```python
import torch

def _softmax(x, axis=-1):
    return torch.softmax(x, dim=axis)

def _gelu(x):
    return torch.nn.functional.gelu(x, approximate='tanh')

def _silu(x):
    return torch.nn.functional.silu(x)

def _sigmoid(x):
    return torch.sigmoid(x)

def _layernorm(x, axis=-1, eps=1e-05):
    m = x.mean(dim=axis, keepdim=True)
    v = x.var(dim=axis, keepdim=True, unbiased=False)
    return (x - m) / torch.sqrt(v + eps)

def _scatter_add(tgt, idx, src, axis=0):
    return tgt.clone().index_add_(axis, idx, src)

def _segment_sum(src, seg, n):
    out = torch.zeros((n,) + src.shape[1:], dtype=src.dtype)
    return out.index_add_(0, seg, src)

def _pad(x, pw):
    flat = tuple((v for pair in reversed(pw) for v in pair))
    return torch.nn.functional.pad(x, flat)
kernel_name = 'adaLN_cond__sliding_block_cached__moe_arch_mod__prompt'

def setup_inputs():

    _w = lambda a: (lambda t: t.to(torch.bfloat16) if t.is_floating_point() else t)(torch.as_tensor(a))

    def _A_setup():
        B, Sq, D = (1, 2048, 1024)
        Hq, Hkv, Sk, Dh = (32, 4, 2048, 128)
        assert Hq % Hkv == 0, (Hq, Hkv)
        return {'x': _w((lambda *s: torch.randn(*s, dtype=torch.bfloat16) * 0.05)(B, Sq, D)), 'k_cache': _w((lambda *s: torch.randn(*s, dtype=torch.bfloat16) * 3.2)(B, Hkv, Sk, Dh)), 'v_cache': _w((lambda *s: torch.randn(*s, dtype=torch.bfloat16) * 0.4)(B, Hkv, Sk, Dh)), 'wq': _w((lambda *s: torch.randn(*s, dtype=torch.bfloat16) * 3.2)(D, Hq * Dh) * D ** (-0.5)), 'wo': _w((lambda *s: torch.randn(*s, dtype=torch.bfloat16) * 0.4)(Hq * Dh, D) * (Hq * Dh) ** (-0.5))}
    _A_in = _A_setup()

    def _B_setup():
        B, S, D, F, C = (1, 2048, 1024, 3584, 1)
        return {'x': _w((lambda *s: torch.randn(*s, dtype=torch.bfloat16) * 0.05)(B, S, D)), 'w_r': _w((lambda *s: torch.randn(*s, dtype=torch.bfloat16) * 0.05)(D)), 'w_gate': _w((lambda *s: torch.randn(*s, dtype=torch.bfloat16) * 0.05)(D, F)), 'w_up': _w((lambda *s: torch.randn(*s, dtype=torch.bfloat16) * 0.05)(D, F)), 'w_down': _w((lambda *s: torch.randn(*s, dtype=torch.bfloat16) * 0.05)(F, D))}
    _B_in = _B_setup()
    return {'A_x': _A_in['x'], 'A_k_cache': _A_in['k_cache'], 'A_v_cache': _A_in['v_cache'], 'A_wq': _A_in['wq'], 'A_wo': _A_in['wo'], 'B_x': _B_in['x'], 'B_w_r': _B_in['w_r'], 'B_w_gate': _B_in['w_gate'], 'B_w_up': _B_in['w_up'], 'B_w_down': _B_in['w_down'], 'c': _w((lambda *s: torch.randn(*s, dtype=torch.bfloat16) * 0.1)(1, 1024) * 8.0), 'w_mod': _w((lambda *s: torch.randn(*s, dtype=torch.bfloat16) * 0.1)(1024, 6 * 1024) * 1024 ** (-0.5) * 8.0)}

def reference(A_x, A_k_cache, A_v_cache, A_wq, A_wo, B_x, B_w_r, B_w_gate, B_w_up, B_w_down, c, w_mod):

    def _A_ref(x, k_cache, v_cache, wq, wo):
        B, Sq, D = x.shape
        Hq, Dh = (32, 128)
        Hkv, Sk = (k_cache.shape[1], k_cache.shape[2])
        W = min(4096, max(256, Sk // 4))
        rep = Hq // Hkv
        q = (lambda x, *d: x.permute(*d))((x @ wq).reshape(B, Sq, Hq, Dh), 0, 2, 1, 3)
        k = (lambda x, n, axis: torch.repeat_interleave(x, n, dim=axis))(k_cache[:, :, Sk - W:, :], rep, axis=1)
        v = (lambda x, n, axis: torch.repeat_interleave(x, n, dim=axis))(v_cache[:, :, Sk - W:, :], rep, axis=1)
        scores = torch.einsum('bhqd,bhkd->bhqk', q, k) * Dh ** (-0.5)
        p = _softmax(scores, axis=-1)
        o = torch.einsum('bhqk,bhkd->bhqd', p, v)
        return (lambda x, *d: x.permute(*d))(o, 0, 2, 1, 3).reshape(B, Sq, Hq * Dh) @ wo

    def _B_ref(x, w_r, w_gate, w_up, w_down):
        B, S, D = x.shape
        C = 1
        r = x @ w_r
        idx = torch.argsort(-r, axis=-1)[:, :C]
        idx_e = (lambda x, n, axis: torch.repeat_interleave(x, n, dim=axis))(idx.reshape(B, C, 1), D, axis=2)
        x_sel = (lambda x, i, axis: torch.take_along_dim(x, i, dim=axis))(x, idx_e, axis=1)
        g = _silu(x_sel @ w_gate)
        u = x_sel @ w_up
        y = g * u @ w_down
        r_sel = _sigmoid((lambda x, i, axis: torch.take_along_dim(x, i, dim=axis))(r, idx, axis=1))
        y = y * r_sel.reshape(B, C, 1)
        b_off = (torch.arange(B) * S).reshape(B, 1)
        flat_idx = (idx + b_off).reshape(B * C)
        zero = (x * 0.0).reshape(B * S, D)
        upd = _scatter_add(zero, flat_idx, y.reshape(B * C, D), axis=0)
        return x + upd.reshape(B, S, D)
    x = A_x
    mod = (_silu(c) @ w_mod).reshape(c.shape[0], 6, 1, -1)
    sa, ca, ga, sb, cb, gb = (mod[:, 0].clone(), mod[:, 1].clone(), mod[:, 2].clone(), mod[:, 3].clone(), mod[:, 4].clone(), mod[:, 5].clone())
    h = _layernorm(x, axis=-1) * (1 + ca) + sa
    x = x + ga * _A_ref(h, A_k_cache, A_v_cache, A_wq, A_wo)
    h = _layernorm(x, axis=-1) * (1 + cb) + sb
    x = x + gb * _B_ref(h, B_w_r, B_w_gate, B_w_up, B_w_down)
    return x
```

```cpp
#include <cuda_runtime.h>
#include <cuda_bf16.h>
#include <cuda.h>
#include <stdint.h>
#include <type_traits>

#define HD 1
#define HDX 2
#define XF 4
#define XE 32
#define XR 16
#define PF2 2
#define PF2T 2
#define NRS 6
#define FPACE 2
#define GOST 24
#define WB 2
#define WN 16
#define E0 3

namespace {

constexpr int SEQ = 2048, DM = 1024, NQ = 4096, SK = 2048, WIN = 512, FF = 3584, NMOD = 6144;
constexpr int NMAIN = 128, NHELP = 4, NFFN = 112;
constexpr int NSLOT = 4, SLOT_BYTES = 32768, UNIT = 16384, GST_BYTES = 3 * UNIT;
constexpr uint32_t XT0 = 0x9630, XT1 = 0x54DC, XT2 = 0xDC96;
constexpr uint32_t WT0 = 0xA741, WT1 = 0x720A, WT2 = 0x20A7;
constexpr uint32_t AT0 = 0x7420, AT1 = 0x2C0A;
constexpr uint32_t QT = 0x549696DC;
constexpr int OFF_STAGE = 12 * UNIT;
constexpr int OFF_RES = 4 * UNIT, OFF_GATE = 6 * UNIT;
constexpr int OFF_PAR = 14 * UNIT;
constexpr int OFF_BAR = OFF_PAR + 2048 + 512;
constexpr int SMEM_BYTES = OFF_BAR + 512;
static_assert(SMEM_BYTES <= 232448, "smem");

constexpr int PAR_GA = 0, PAR_CB1 = 256, PAR_SB = 512, PAR_GB = 768;
constexpr int PAR_A = 1024;
constexpr int PAR_CONST = 1536;
constexpr int PAR_RED = 1600;
constexpr int PAR_SINK = 2176;

struct Maps {
  CUtensorMap x, wq, k, v, wo, wg, wu, wd, wm;
};
struct Ptrs {
  const __nv_bfloat16 *x, *w_r, *c, *w_mod, *w_gate, *w_up, *w_down;
  __nv_bfloat16* out;
};

__device__ __align__(1024) uint8_t g_h[SEQ * DM * 2];
__device__ __align__(1024) uint8_t g_o[SEQ * NQ * 2];
__device__ __align__(128) uint32_t g_mod[NMOD];
__device__ __align__(128) uint32_t g_modp[2 * 2 * DM];
__device__ __align__(128) uint32_t g_ln1[SEQ * 4];
__device__ __align__(128) uint32_t g_cnt_h[16 * 32];
__device__ __align__(128) uint32_t g_cnt_o[128 * 32];
__device__ __align__(128) uint32_t g_xch[NMAIN * 8 * 256 * 4];
__device__ __align__(128) uint32_t g_stats[8 * SEQ * 4];
__device__ __align__(128) uint32_t g_cand[16 * 8];
__device__ __align__(128) uint32_t g_row[16 * 2 * DM];
__device__ __align__(128) uint32_t g_ypart[NMAIN * NFFN * 8];
__device__ uint32_t g_epoch;

__device__ __forceinline__ uint32_t fresh_lane() { uint32_t l; asm volatile("mov.u32 %0, %%laneid;" : "=r"(l)); return l; }
__device__ __forceinline__ uint32_t frag_offset(int warp) {
  const uint32_t l = fresh_lane();
  return ((warp & 3) * 16 + (l & 15)) * 128 + (((l >> 4) ^ (l & 7)) << 4);
}
__device__ __forceinline__ uint32_t smem_u32(const void* p) { return (uint32_t)__cvta_generic_to_shared(p); }
__device__ __forceinline__ void mbar_init(uint32_t bar, uint32_t cnt) {
  asm volatile("mbarrier.init.shared::cta.b64 [%0], %1;" ::"r"(bar), "r"(cnt) : "memory");
}
__device__ __forceinline__ void mbar_expect_tx(uint32_t bar, uint32_t bytes) {
  asm volatile("mbarrier.arrive.expect_tx.shared::cta.b64 _, [%0], %1;" ::"r"(bar), "r"(bytes) : "memory");
}
__device__ __forceinline__ void mbar_arrive(uint32_t bar) {
  asm volatile("mbarrier.arrive.shared::cta.b64 _, [%0];" ::"r"(bar) : "memory");
}
__device__ __forceinline__ void mbar_arrive_pred(uint32_t bar, bool p) {
  asm volatile("{ .reg .pred p; setp.ne.b32 p, %1, 0; @p mbarrier.arrive.shared::cta.b64 _, [%0]; }" ::"r"(bar), "r"((int)p) : "memory");
}
__device__ __forceinline__ void mbar_arrive_cl(uint32_t bar, bool p) {
  asm volatile("{ .reg .pred p; setp.ne.b32 p, %1, 0; @p mbarrier.arrive.shared::cluster.b64 _, [%0]; }" ::"r"(bar), "r"((int)p) : "memory");
}
__device__ __forceinline__ uint32_t mapa(uint32_t addr, uint32_t cta) {
  uint32_t r; asm("mapa.shared::cluster.u32 %0, %1, %2;" : "=r"(r) : "r"(addr), "r"(cta)); return r;
}
__device__ __forceinline__ void cluster_arrive() { asm volatile("barrier.cluster.arrive.relaxed.aligned;" ::: "memory"); }
__device__ __forceinline__ void cluster_wait() { asm volatile("barrier.cluster.wait.aligned;" ::: "memory"); }
__device__ __forceinline__ void watchdog(uint32_t& n) {
  asm volatile("{\n.reg .pred q;\n.reg .u64 z;\nadd.u32 %0, %0, 1;\nsetp.gt.u32 q, %0, 0x1000000;\nmov.u64 z, 0;\n@q st.global.u32 [z], %0;\n}" : "+r"(n)::"memory");
}
__device__ __forceinline__ void mbar_wait(uint32_t bar, uint32_t parity) {
  asm volatile(
      "{\n.reg .pred p, q;\n.reg .u32 n;\n.reg .u64 z;\nmov.u32 n, 0;\nmov.u64 z, 0;\n"
      "WAIT_%=:\n"
      "mbarrier.try_wait.parity.shared::cta.b64 p, [%0], %1;\n"
      "@p bra DONE_%=;\n"
      "add.u32 n, n, 1;\n"
      "setp.gt.u32 q, n, 0x400000;\n"
      "@q st.global.u32 [z], n;\n"
      "bra WAIT_%=;\n"
      "DONE_%=:\n}" ::"r"(bar), "r"(parity) : "memory");
}
__device__ __forceinline__ bool mbar_test(uint32_t bar, uint32_t parity) {
  uint32_t ok;
  asm volatile("{\n.reg .pred p;\nmbarrier.test_wait.parity.shared::cta.b64 p, [%1], %2;\nselp.u32 %0, 1, 0, p;\n}" : "=r"(ok) : "r"(bar), "r"(parity) : "memory");
  return ok;
}
__device__ __forceinline__ uint64_t l2_stream() {
  uint64_t f; asm("createpolicy.fractional.L2::evict_first.b64 %0, 1.0;" : "=l"(f)); return f;
}
__device__ __forceinline__ void tma2d(uint32_t dst, const CUtensorMap* m, int c0, int c1, uint32_t bar) {
  asm volatile("cp.async.bulk.tensor.2d.shared::cluster.global.mbarrier::complete_tx::bytes.L2::cache_hint [%0], [%1, {%3, %4}], [%2], %5;"
               ::"r"(dst), "l"(m), "r"(bar), "r"(c0), "r"(c1), "l"(l2_stream()) : "memory");
}
__device__ __forceinline__ void tma3d_prefetch(const CUtensorMap* m, int c0, int c1, int c2) {
  asm volatile("cp.async.bulk.prefetch.tensor.3d.L2.global.tile [%0, {%1, %2, %3}];" ::"l"(m), "r"(c0), "r"(c1), "r"(c2) : "memory");
}
__device__ __forceinline__ void bulk_load(uint32_t dst, const void* src, uint32_t bytes, uint32_t bar) {
  asm volatile("cp.async.bulk.shared::cluster.global.mbarrier::complete_tx::bytes [%0], [%1], %2, [%3];" ::"r"(dst), "l"(src), "r"(bytes), "r"(bar) : "memory");
}
__device__ __forceinline__ void bulk_load_stream(uint32_t dst, const void* src, uint32_t bytes, uint32_t bar) {
  asm volatile("cp.async.bulk.shared::cluster.global.mbarrier::complete_tx::bytes.L2::cache_hint [%0], [%1], %2, [%3], %4;"
               ::"r"(dst), "l"(src), "r"(bytes), "r"(bar), "l"(l2_stream()) : "memory");
}
__device__ __forceinline__ void bulk_store(void* dst, uint32_t src, uint32_t bytes) {
  asm volatile("cp.async.bulk.global.shared::cta.bulk_group [%0], [%1], %2;" ::"l"(dst), "r"(src), "r"(bytes) : "memory");
}
__device__ __forceinline__ uint32_t unit_of(uint32_t table, uint32_t i) { return ((table >> (i * 4)) & 15) * UNIT; }
__device__ __forceinline__ void tma3d(uint32_t dst, const CUtensorMap* m, int c0, int c1, int c2, uint32_t bar) {
  asm volatile("cp.async.bulk.tensor.3d.shared::cluster.global.mbarrier::complete_tx::bytes.L2::cache_hint [%0], [%1, {%3, %4, %5}], [%2], %6;"
               ::"r"(dst), "l"(m), "r"(bar), "r"(c0), "r"(c1), "r"(c2), "l"(l2_stream()) : "memory");
}
template <bool STREAM>
__device__ __forceinline__ void tma3d_mc(uint32_t dst, const CUtensorMap* m, int c0, int c1, int c2, uint32_t bar) {
  if (STREAM)
    asm volatile("cp.async.bulk.tensor.3d.shared::cluster.global.mbarrier::complete_tx::bytes.multicast::cluster.L2::cache_hint [%0], [%1, {%3, %4, %5}], [%2], %6, %7;"
                 ::"r"(dst), "l"(m), "r"(bar), "r"(c0), "r"(c1), "r"(c2), "h"((uint16_t)3), "l"(l2_stream()) : "memory");
  else
    asm volatile("cp.async.bulk.tensor.3d.shared::cluster.global.mbarrier::complete_tx::bytes.multicast::cluster [%0], [%1, {%3, %4, %5}], [%2], %6;"
                 ::"r"(dst), "l"(m), "r"(bar), "r"(c0), "r"(c1), "r"(c2), "h"((uint16_t)3) : "memory");
}
__device__ __forceinline__ void prefetch_map(const CUtensorMap* m) {
  asm volatile("prefetch.tensormap [%0];" ::"l"(m) : "memory");
}
__device__ __forceinline__ void fence_async() { asm volatile("fence.proxy.async.global;" ::: "memory"); }
__device__ __forceinline__ void fence_async_smem() { asm volatile("fence.proxy.async.shared::cta;" ::: "memory"); }
__device__ __forceinline__ void bar_sync(int id, int n) { asm volatile("bar.sync %0, %1;" ::"r"(id), "r"(n) : "memory"); }
__device__ __forceinline__ void bar_arrive(int id, int n) { asm volatile("bar.arrive %0, %1;" ::"r"(id), "r"(n) : "memory"); }
__device__ __forceinline__ void wg_fence() { asm volatile("wgmma.fence.sync.aligned;" ::: "memory"); }
__device__ __forceinline__ void wg_commit() { asm volatile("wgmma.commit_group.sync.aligned;" ::: "memory"); }
template <int N> __device__ __forceinline__ void wg_wait() { asm volatile("wgmma.wait_group.sync.aligned %0;" ::"n"(N) : "memory"); }
__device__ __forceinline__ uint64_t make_desc(uint32_t addr, uint32_t lbo, uint32_t sbo) {
  return (uint64_t)((addr & 0x3FFFF) >> 4) | ((uint64_t)(lbo >> 4) << 16) | ((uint64_t)(sbo >> 4) << 32) | (1ull << 62);
}
__device__ __forceinline__ uint32_t ld_relaxed(const uint32_t* p) {
  uint32_t v; asm volatile("ld.relaxed.gpu.global.u32 %0, [%1];" : "=r"(v) : "l"(p) : "memory"); return v;
}
__device__ __forceinline__ uint32_t ld_acquire(const uint32_t* p) {
  uint32_t v; asm volatile("ld.acquire.gpu.global.u32 %0, [%1];" : "=r"(v) : "l"(p) : "memory"); return v;
}
__device__ __forceinline__ uint4 ld_relaxed4(const uint32_t* p) {
  uint4 v; asm volatile("ld.relaxed.gpu.global.v4.u32 {%0,%1,%2,%3}, [%4];" : "=r"(v.x), "=r"(v.y), "=r"(v.z), "=r"(v.w) : "l"(p) : "memory"); return v;
}
__device__ __forceinline__ uint2 ld_relaxed2(const uint32_t* p) {
  uint2 v; asm volatile("ld.relaxed.gpu.global.v2.u32 {%0,%1}, [%2];" : "=r"(v.x), "=r"(v.y) : "l"(p) : "memory"); return v;
}
__device__ __forceinline__ void st_relaxed(uint32_t* p, uint32_t v) {
  asm volatile("st.relaxed.gpu.global.u32 [%0], %1;" ::"l"(p), "r"(v) : "memory");
}
__device__ __forceinline__ void st_relaxed2(uint32_t* p, uint32_t a, uint32_t b) {
  asm volatile("st.relaxed.gpu.global.v2.u32 [%0], {%1,%2};" ::"l"(p), "r"(a), "r"(b) : "memory");
}
__device__ __forceinline__ void st_relaxed4(uint32_t* p, uint32_t a, uint32_t b, uint32_t c, uint32_t d) {
  asm volatile("st.relaxed.gpu.global.v4.u32 [%0], {%1,%2,%3,%4};" ::"l"(p), "r"(a), "r"(b), "r"(c), "r"(d) : "memory");
}
__device__ __forceinline__ void st_b128(uint32_t* p, uint32_t a, uint32_t b, uint32_t c, uint32_t d) {
  asm volatile("{ .reg .b64 u, v; .reg .b128 w; mov.b64 u, {%1, %2}; mov.b64 v, {%3, %4}; mov.b128 w, {u, v}; st.relaxed.gpu.global.b128 [%0], w; }"
               ::"l"(p), "r"(a), "r"(b), "r"(c), "r"(d) : "memory");
}
__device__ __forceinline__ uint4 ld_b128(const uint32_t* p) {
  uint4 r;
  asm volatile("{ .reg .b64 u, v; .reg .b128 w; ld.relaxed.gpu.global.b128 w, [%4]; mov.b128 {u, v}, w; mov.b64 {%0, %1}, u; mov.b64 {%2, %3}, v; }"
               : "=r"(r.x), "=r"(r.y), "=r"(r.z), "=r"(r.w) : "l"(p) : "memory");
  return r;
}
__device__ __forceinline__ void st_pairs(uint32_t* p, uint32_t a, uint32_t b, uint32_t tag) {
  asm volatile("{ .reg .b64 u, v; mov.b64 u, {%1, %3}; mov.b64 v, {%2, %3}; st.relaxed.gpu.global.v2.b64 [%0], {u, v}; }"
               ::"l"(p), "r"(a), "r"(b), "r"(tag) : "memory");
}
__device__ __forceinline__ uint4 ld_pairs(const uint32_t* p) {
  uint4 v;
  asm volatile("{ .reg .b64 u, v; ld.relaxed.gpu.global.v2.b64 {u, v}, [%4]; mov.b64 {%0, %1}, u; mov.b64 {%2, %3}, v; }"
               : "=r"(v.x), "=r"(v.y), "=r"(v.z), "=r"(v.w) : "l"(p) : "memory");
  return v;
}
__device__ __forceinline__ uint2 ld_pair(const uint32_t* p) {
  uint2 v;
  asm volatile("{ .reg .b64 u; ld.relaxed.gpu.global.b64 u, [%2]; mov.b64 {%0, %1}, u; }" : "=r"(v.x), "=r"(v.y) : "l"(p) : "memory");
  return v;
}
__device__ __forceinline__ void red_release(uint32_t* p, uint32_t v) {
  asm volatile("red.release.gpu.global.add.u32 [%0], %1;" ::"l"(p), "r"(v) : "memory");
}
__device__ __forceinline__ uint32_t ldg_nc1(const void* p) {
  uint32_t v;
  asm volatile("ld.global.nc.u32 %0, [%1];" : "=r"(v) : "l"(p));
  return v;
}
__device__ __forceinline__ uint4 ldg_nc4(const void* p) {
  uint4 v; asm volatile("ld.global.nc.L1::no_allocate.v4.u32 {%0,%1,%2,%3}, [%4];" : "=r"(v.x), "=r"(v.y), "=r"(v.z), "=r"(v.w) : "l"(p)); return v;
}
__device__ __forceinline__ void stg4(void* p, uint4 v) {
  asm volatile("st.global.v4.u32 [%0], {%1,%2,%3,%4};" ::"l"(p), "r"(v.x), "r"(v.y), "r"(v.z), "r"(v.w) : "memory");
}
__device__ __forceinline__ void wait_counter(const uint32_t* p, uint32_t target) {
  uint32_t n = 0;
  while ((int)(ld_acquire(p) - target) < 0) { watchdog(n); }
}
__device__ __forceinline__ uint32_t tagf(float v, uint32_t tag) { return (__float_as_uint(v) & ~3u) | tag; }
__device__ __forceinline__ bool tag_ok(uint4 v, uint32_t tag) { return (((v.x ^ tag) | (v.y ^ tag) | (v.z ^ tag) | (v.w ^ tag)) & 3u) == 0; }
__device__ __forceinline__ float untag_sum(uint32_t a, uint32_t b) { return __uint_as_float(a & ~3u) + __uint_as_float(b & ~3u); }
__device__ __forceinline__ uint4 poll4(const uint32_t* p, uint32_t tag) {
  uint4 v = ld_relaxed4(p);
  uint32_t n = 0;
  while (!tag_ok(v, tag)) { v = ld_relaxed4(p); watchdog(n); }
  return v;
}
__device__ __forceinline__ float bf_lo(uint32_t v) { return __uint_as_float(v << 16); }
__device__ __forceinline__ float bf_hi(uint32_t v) { return __uint_as_float(v & 0xffff0000u); }
__device__ __forceinline__ uint32_t pack_bf(float lo, float hi) {
  uint32_t r; asm("cvt.rn.bf16x2.f32 %0, %1, %2;" : "=r"(r) : "f"(hi), "f"(lo)); return r;
}
__device__ __forceinline__ float rbf(float v) { return __uint_as_float(pack_bf(0.f, v) & 0xffff0000u); }
__device__ __forceinline__ uint32_t hmul2(uint32_t a, uint32_t b) {
  uint32_t r; asm("mul.rn.bf16x2 %0, %1, %2;" : "=r"(r) : "r"(a), "r"(b)); return r;
}
__device__ __forceinline__ uint32_t hadd2(uint32_t a, uint32_t b) {
  uint32_t r; asm("add.rn.bf16x2 %0, %1, %2;" : "=r"(r) : "r"(a), "r"(b)); return r;
}
__device__ __forceinline__ uint32_t hsub2(uint32_t a, uint32_t b) {
  uint32_t r; asm("sub.rn.bf16x2 %0, %1, %2;" : "=r"(r) : "r"(a), "r"(b)); return r;
}
__device__ __forceinline__ uint32_t hmax2(uint32_t a, uint32_t b) {
  uint32_t r; asm("max.bf16x2 %0, %1, %2;" : "=r"(r) : "r"(a), "r"(b)); return r;
}
__device__ __forceinline__ float ex2(float x) { float r; asm("ex2.approx.ftz.f32 %0, %1;" : "=f"(r) : "f"(x)); return r; }
__device__ __forceinline__ void stmatrix4(uint32_t addr, uint32_t a, uint32_t b, uint32_t c, uint32_t d) {
  asm volatile("stmatrix.sync.aligned.m8n8.x4.shared.b16 [%0], {%1,%2,%3,%4};" ::"r"(addr), "r"(a), "r"(b), "r"(c), "r"(d) : "memory");
}
__device__ __forceinline__ void ldmatrix4(uint32_t addr, uint32_t& a, uint32_t& b, uint32_t& c, uint32_t& d) {
  asm volatile("ldmatrix.sync.aligned.m8n8.x4.shared.b16 {%0,%1,%2,%3}, [%4];" : "=r"(a), "=r"(b), "=r"(c), "=r"(d) : "r"(addr) : "memory");
}
__device__ __forceinline__ void ldmatrix4t(uint32_t addr, uint32_t& a, uint32_t& b, uint32_t& c, uint32_t& d) {
  asm volatile("ldmatrix.sync.aligned.m8n8.x4.trans.shared.b16 {%0,%1,%2,%3}, [%4];" : "=r"(a), "=r"(b), "=r"(c), "=r"(d) : "r"(addr) : "memory");
}
__device__ __forceinline__ void mma16816(float (&d)[4], uint32_t a0, uint32_t a1, uint32_t a2, uint32_t a3, uint32_t b0, uint32_t b1) {
  asm volatile("mma.sync.aligned.m16n8k16.row.col.f32.bf16.bf16.f32 {%0,%1,%2,%3}, {%4,%5,%6,%7}, {%8,%9}, {%0,%1,%2,%3};"
               : "+f"(d[0]), "+f"(d[1]), "+f"(d[2]), "+f"(d[3]) : "r"(a0), "r"(a1), "r"(a2), "r"(a3), "r"(b0), "r"(b1));
}
__device__ __forceinline__ void sts1(uint32_t a, uint32_t v) { asm volatile("st.shared.u32 [%0], %1;" ::"r"(a), "r"(v) : "memory"); }
__device__ __forceinline__ uint4 lds4(uint32_t a) {
  uint4 v; asm volatile("ld.shared.v4.u32 {%0,%1,%2,%3}, [%4];" : "=r"(v.x), "=r"(v.y), "=r"(v.z), "=r"(v.w) : "r"(a) : "memory"); return v;
}
__device__ __forceinline__ uint2 lds2(uint32_t a) {
  uint2 v; asm volatile("ld.shared.v2.u32 {%0,%1}, [%2];" : "=r"(v.x), "=r"(v.y) : "r"(a) : "memory"); return v;
}
__device__ __forceinline__ uint32_t lds1(uint32_t a) {
  uint32_t v; asm volatile("ld.shared.u32 %0, [%1];" : "=r"(v) : "r"(a) : "memory"); return v;
}
__device__ __forceinline__ void sts2(uint32_t a, uint32_t x, uint32_t y) { asm volatile("st.shared.v2.u32 [%0], {%1,%2};" ::"r"(a), "r"(x), "r"(y) : "memory"); }
__device__ __forceinline__ void sts4(uint32_t a, uint4 v) {
  asm volatile("st.shared.v4.u32 [%0], {%1,%2,%3,%4};" ::"r"(a), "r"(v.x), "r"(v.y), "r"(v.z), "r"(v.w) : "memory");
}
__device__ __forceinline__ float silu_f(float v) { return __fdividef(v, 1.f + __expf(-v)); }
__device__ __forceinline__ uint32_t hfma2(uint32_t a, uint32_t b, uint32_t c) {
  uint32_t r; asm("fma.rn.bf16x2 %0, %1, %2, %3;" : "=r"(r) : "r"(a), "r"(b), "r"(c)); return r;
}
__device__ __forceinline__ void split_inv(float sd, uint32_t& ih, uint32_t& il) {
  const float inv = 1.f / sd;
  ih = pack_bf(inv, inv);
  const float lo = inv - bf_lo(ih);
  il = pack_bf(lo, lo);
}
__device__ __forceinline__ uint32_t ln_mod(uint32_t x, uint32_t mean2, uint32_t ih, uint32_t il, uint32_t c1, uint32_t sh) {
  const uint32_t d = hsub2(x, mean2);
  return hadd2(hmul2(hfma2(d, ih, hmul2(d, il)), c1), sh);
}

#define R8(a, i) "+f"(a[i]), "+f"(a[i + 1]), "+f"(a[i + 2]), "+f"(a[i + 3]), "+f"(a[i + 4]), "+f"(a[i + 5]), "+f"(a[i + 6]), "+f"(a[i + 7])
#define D64 "{%0,%1,%2,%3,%4,%5,%6,%7,%8,%9,%10,%11,%12,%13,%14,%15,%16,%17,%18,%19,%20,%21,%22,%23,%24,%25,%26,%27,%28,%29,%30,%31," \
            "%32,%33,%34,%35,%36,%37,%38,%39,%40,%41,%42,%43,%44,%45,%46,%47,%48,%49,%50,%51,%52,%53,%54,%55,%56,%57,%58,%59,%60,%61,%62,%63}"
template <int TB>
__device__ __forceinline__ void mma_ss(float (&d)[64], uint64_t da, uint64_t db, int sc) {
  asm volatile("{\n.reg .pred p;\nsetp.ne.b32 p, %66, 0;\n"
               "wgmma.mma_async.sync.aligned.m64n128k16.f32.bf16.bf16 " D64 ", %64, %65, p, 1, 1, 0, %67;\n}"
               : R8(d, 0), R8(d, 8), R8(d, 16), R8(d, 24), R8(d, 32), R8(d, 40), R8(d, 48), R8(d, 56)
               : "l"(da), "l"(db), "r"(sc), "n"(TB));
}
template <int TB>
__device__ __forceinline__ void mma_rs(float (&d)[64], uint32_t a0, uint32_t a1, uint32_t a2, uint32_t a3, uint64_t db, int sc) {
  asm volatile("{\n.reg .pred p;\nsetp.ne.b32 p, %69, 0;\n"
               "wgmma.mma_async.sync.aligned.m64n128k16.f32.bf16.bf16 " D64 ", {%64,%65,%66,%67}, %68, p, 1, 1, %70;\n}"
               : R8(d, 0), R8(d, 8), R8(d, 16), R8(d, 24), R8(d, 32), R8(d, 40), R8(d, 48), R8(d, 56)
               : "r"(a0), "r"(a1), "r"(a2), "r"(a3), "l"(db), "r"(sc), "n"(TB));
}
#define D128 "{%0,%1,%2,%3,%4,%5,%6,%7,%8,%9,%10,%11,%12,%13,%14,%15,%16,%17,%18,%19,%20,%21,%22,%23,%24,%25,%26,%27,%28,%29,%30,%31," \
             "%32,%33,%34,%35,%36,%37,%38,%39,%40,%41,%42,%43,%44,%45,%46,%47,%48,%49,%50,%51,%52,%53,%54,%55,%56,%57,%58,%59,%60,%61,%62,%63," \
             "%64,%65,%66,%67,%68,%69,%70,%71,%72,%73,%74,%75,%76,%77,%78,%79,%80,%81,%82,%83,%84,%85,%86,%87,%88,%89,%90,%91,%92,%93,%94,%95," \
             "%96,%97,%98,%99,%100,%101,%102,%103,%104,%105,%106,%107,%108,%109,%110,%111,%112,%113,%114,%115,%116,%117,%118,%119,%120,%121,%122,%123,%124,%125,%126,%127}"
#define R128(d, e) R8(d, 0), R8(d, 8), R8(d, 16), R8(d, 24), R8(d, 32), R8(d, 40), R8(d, 48), R8(d, 56), \
                   R8(e, 0), R8(e, 8), R8(e, 16), R8(e, 24), R8(e, 32), R8(e, 40), R8(e, 48), R8(e, 56)
__device__ __forceinline__ void mma256_ss(float (&d)[64], float (&e)[64], uint64_t da, uint64_t db, int sc) {
  asm volatile("{\n.reg .pred p;\nsetp.ne.b32 p, %130, 0;\n"
               "wgmma.mma_async.sync.aligned.m64n256k16.f32.bf16.bf16 " D128 ", %128, %129, p, 1, 1, 0, 1;\n}"
               : R128(d, e) : "l"(da), "l"(db), "r"(sc));
}
__device__ __forceinline__ void mma256_rs(float (&d)[64], float (&e)[64], uint32_t a0, uint32_t a1, uint32_t a2, uint32_t a3, uint64_t db) {
  asm volatile("{\n.reg .pred p;\nsetp.ne.b32 p, 1, 0;\n"
               "wgmma.mma_async.sync.aligned.m64n256k16.f32.bf16.bf16 " D128 ", {%128,%129,%130,%131}, %132, p, 1, 1, 1;\n}"
               : R128(d, e) : "r"(a0), "r"(a1), "r"(a2), "r"(a3), "l"(db));
}
template <int N> __device__ __forceinline__ void keep(float (&a)[N]) {
#pragma unroll
  for (int i = 0; i < N; i++) asm volatile("" : "+f"(a[i])::"memory");
}
template <int N> __device__ __forceinline__ void keep(uint32_t (&a)[N]) {
#pragma unroll
  for (int i = 0; i < N; i++) asm volatile("" : "+r"(a[i])::"memory");
}

#define PROF(cond, idx) do {} while (0)

constexpr float SCL2 = 1.4426950408889634f * 0.08838834764831845f;

__device__ __forceinline__ void pack_p(const float (&s)[64], uint32_t (&p)[32]) {
#pragma unroll
  for (int i = 0; i < 32; i++) p[i] = pack_bf(s[2 * i], s[2 * i + 1]);
}

__device__ __forceinline__ void issue_qk(float (&s)[64], uint32_t q0, uint32_t q1, uint32_t kslot) {
  const uint64_t db = make_desc(kslot, 16, 1024), da0 = make_desc(q0, 16, 1024), da1 = make_desc(q1, 16, 1024);
#pragma unroll
  for (int kk = 0; kk < 8; kk++) mma_ss<0>(s, (kk < 4 ? da0 : da1) + (kk & 3) * 2, db + (kk >> 2) * 1024 + (kk & 3) * 2, kk != 0);
}
__device__ __forceinline__ void issue_pv(float (&o)[64], uint32_t (&p)[32], uint32_t vslot, int acc) {
  uint64_t db = make_desc(vslot, 16384, 1024);
#pragma unroll
  for (int kk = 0; kk < 8; kk++)
    mma_rs<1>(o, p[4 * kk], p[4 * kk + 1], p[4 * kk + 2], p[4 * kk + 3], db + kk * 128, kk == 0 ? acc : 1);
}

template <int H>
__device__ __forceinline__ void store_chunk(const float (&a)[64], uint32_t addr) {
#pragma unroll
  for (int i = 8 * H; i < 8 * H + 8; i += 2)
    stmatrix4(addr ^ ((i & 7) << 4), pack_bf(a[4 * i], a[4 * i + 1]), pack_bf(a[4 * i + 2], a[4 * i + 3]),
              pack_bf(a[4 * i + 4], a[4 * i + 5]), pack_bf(a[4 * i + 6], a[4 * i + 7]));
}
template <int H>
__device__ __forceinline__ void store_chunk(const float (&a)[64], float i0, float i1, uint32_t addr) {
#pragma unroll
  for (int i = 8 * H; i < 8 * H + 8; i += 2)
    stmatrix4(addr ^ ((i & 7) << 4), pack_bf(a[4 * i] * i0, a[4 * i + 1] * i0), pack_bf(a[4 * i + 2] * i1, a[4 * i + 3] * i1),
              pack_bf(a[4 * i + 4] * i0, a[4 * i + 5] * i0), pack_bf(a[4 * i + 6] * i1, a[4 * i + 7] * i1));
}
__device__ __forceinline__ float inv_quad_sum(float l) {
  l += __shfl_xor_sync(0xffffffffu, l, 1);
  l += __shfl_xor_sync(0xffffffffu, l, 2);
  return __fdividef(1.f, l);
}

__device__ __forceinline__ void ln_scalars(float mean, float var, float& mb, float& sd) {
  mb = rbf(mean);
  sd = rbf(sqrtf(rbf(rbf(var) + 1e-5f)));
}

__global__ void __cluster_dims__(2, 1, 1) __launch_bounds__(384, 1) fused_kernel(const __grid_constant__ Maps maps, const Ptrs P) {
  extern __shared__ __align__(1024) uint8_t smem_raw[];
  const uint32_t base = smem_u32(smem_raw);
  const int tid = threadIdx.x, lane = tid & 31;
  const int warp = __shfl_sync(0xffffffffu, tid >> 5, 0);
  const int b = blockIdx.x;
  PROF(tid == 0, 0);

  if (b >= NMAIN) {
    float* sc = reinterpret_cast<float*>(smem_raw);
    float* red = sc + DM;
    for (int k = tid; k < DM; k += 384) sc[k] = rbf(silu_f(__bfloat162float(P.c[k])));
    __syncthreads();
    if (tid < 256) {
      const int col = 2048 + (b - NMAIN) * 1024 + (tid & 127) * 8, r0 = (tid >> 7) * 512;
      float acc[8];
#pragma unroll
      for (int e = 0; e < 8; e++) acc[e] = 0.f;
      for (int r = r0; r < r0 + 512; r += 32) {
        uint4 w[32];
#pragma unroll
        for (int u = 0; u < 32; u++) w[u] = ldg_nc4(P.w_mod + (size_t)(r + u) * NMOD + col);
#pragma unroll
        for (int u = 0; u < 32; u++) {
          float s = sc[r + u];
          acc[0] += s * bf_lo(w[u].x); acc[1] += s * bf_hi(w[u].x); acc[2] += s * bf_lo(w[u].y); acc[3] += s * bf_hi(w[u].y);
          acc[4] += s * bf_lo(w[u].z); acc[5] += s * bf_hi(w[u].z); acc[6] += s * bf_lo(w[u].w); acc[7] += s * bf_hi(w[u].w);
        }
      }
      if (tid >= 128) {
#pragma unroll
        for (int e = 0; e < 8; e++) red[(tid & 127) * 8 + e] = acc[e];
      }
      const uint32_t tag = ld_relaxed(&g_epoch) % 3 + 1;
      bar_sync(1, 256);
      if (tid < 128) {
        uint32_t o[8];
#pragma unroll
        for (int e = 0; e < 8; e++) o[e] = __float_as_uint(rbf(acc[e] + red[tid * 8 + e])) | tag;
        st_relaxed4(g_mod + col, o[0], o[1], o[2], o[3]);
        st_relaxed4(g_mod + col + 4, o[4], o[5], o[6], o[7]);
      }
    }
    PROF(tid == 0, 1);
    return;
  }

  const int rank = b & 1;
  const int rb = ((b >> 4) << 1) | rank, cj = (b >> 1) & 7;
  const uint32_t bfull = base + OFF_BAR, bempty = bfull + NSLOT * 8;
  const uint32_t gfull = bempty + NSLOT * 8, gempty = gfull + 32;
  const uint32_t bar_ofull = gempty + 32;
  const uint32_t bar_ofree = bar_ofull + 16;
  const uint32_t bar_par = bar_ofree + 32;
  const uint32_t bar_mod = bar_par + 8;
  const uint32_t bar_pread = bar_mod + 8;
  const uint32_t bar_xres = bar_pread + 8;
  const uint32_t bar_w1 = bar_xres + 8;
  const uint32_t bar_w2 = bar_w1 + 8;
  const uint32_t bar_last = bar_w2 + 8;
  const uint32_t bar_ring = bar_last + 16;
  const uint32_t bar_box = bar_ring + 8;
  const uint32_t bar_go = bar_box + 96;
  const uint32_t bar_go2 = bar_go + 16;
  const uint32_t bar_cnt = bar_go + 24;
  const uint32_t xfull = bar_go + 32, xempty = xfull + 32;
  const uint32_t bar_hw = xempty + 32, bar_hx = bar_hw + 8;
  const uint32_t bar_hpub = bar_hx + 16;
  const uint32_t bar_ring0 = bar_hpub + 8;
  const uint32_t bar_rst = bar_go + 8;
  const uint32_t stage = base + OFF_STAGE, par = base + OFF_PAR;

  if (tid == 256) {
    for (int s = 0; s < NSLOT; s++) { mbar_init(bfull + s * 8, 1); mbar_init(bempty + s * 8, 16); }
    for (int s = 0; s < 4; s++) { mbar_init(gfull + s * 8, 1); mbar_init(gempty + s * 8, 16); mbar_init(xfull + s * 8, 1); mbar_init(xempty + s * 8, 8); mbar_init(bar_ofree + s * 8, 2); }
    mbar_init(bar_ofull, 128); mbar_init(bar_ofull + 8, 128);
    mbar_init(bar_par, 64); mbar_init(bar_mod, 256); mbar_init(bar_pread, 8); mbar_init(bar_xres, 1);
    mbar_init(bar_w1, 1); mbar_init(bar_w2, 1); mbar_init(bar_last, 1); mbar_init(bar_last + 8, 1); mbar_init(bar_ring, 8); mbar_init(bar_go, 1); mbar_init(bar_go2, 1); mbar_init(bar_cnt, 1); mbar_init(bar_rst, 64); mbar_init(bar_hpub, 8); mbar_init(bar_ring0, 8);
    for (int s = 0; s < 12; s++) mbar_init(bar_box + s * 8, 1);
    asm volatile("fence.mbarrier_init.release.cluster;" ::: "memory");
    prefetch_map(&maps.x); prefetch_map(&maps.wq); prefetch_map(&maps.k); prefetch_map(&maps.v);
  }
  if (tid == 288) {
    mbar_init(bar_hw, 1); mbar_init(bar_hx, 1); mbar_init(bar_hx + 8, 1);
    asm volatile("fence.mbarrier_init.release.cluster;" ::: "memory");
    mbar_expect_tx(bar_hw, 32768);
    mbar_expect_tx(bar_hx, 16384);
    mbar_expect_tx(bar_hx + 8, 16384);
    const __nv_bfloat16* xs = P.x + (size_t)(rb * 128 + cj * 16) * DM;
    bulk_load(base + 2 * GST_BYTES, xs, 16384, bar_hx);
    tma2d(stage, &maps.wm, (b >> 1) * 32, rank * 512, bar_hw);
    tma2d(stage + 16384, &maps.wm, (b >> 1) * 32, rank * 512 + 256, bar_hw);
    bulk_load(base + 3 * GST_BYTES, xs + 8 * DM, 16384, bar_hx + 8);
  }
  cluster_arrive();

  if (warp >= 8) {
    asm volatile("setmaxnreg.dec.sync.aligned.u32 40;");
    if (warp < 10) bar_arrive(1, 320);
    cluster_wait();
    if (warp == 8) {
      if (lane == 0) {
        uint32_t gph = 1;
        const int kvrow = (cj >> 1) * SK + (SK - WIN);
        int wch = cj * 8 + rank * 2;
#pragma unroll 1
        for (int ps = 0; ps < 3; ps++) {
          const CUtensorMap* mw = ps == 2 ? &maps.wo : &maps.wq;
          const uint8_t* xs = ps == 2 ? g_o + (size_t)rb * 64 * UNIT : g_h + (size_t)rb * 16 * UNIT;
          const uint32_t xt = ps == 1 ? XT1 : XT2, wt = ps == 0 ? WT0 : (ps == 1 ? WT1 : WT2);
          const int nst = ps == 2 ? 32 : 16;
          if (ps) {
            const uint32_t epoch = ld_relaxed(&g_epoch);
            wait_counter(ps == 1 ? &g_cnt_h[rb * 32] : &g_cnt_o[(rb * 8 + (cj & 1)) * 32], 8 * (epoch + 1));
            if (ps == 2) wait_counter(&g_cnt_o[(rb * 8 + 2 + (cj & 1)) * 32], 8 * (epoch + 1));
            fence_async();
            mbar_wait(bar_ofree + (ps - 1) * 16, 0);
          }
#pragma unroll 1
          for (int i = 0; i < nst; i++) {
            if (i == GOST) mbar_arrive(bar_go);
            if (ps == 0 && i == HD) mbar_wait(bar_mod, 0);
            if (ps && i && i < 4) mbar_wait(bempty + (i == 3 ? 3 : i - 1) * 8, 1);
            const uint32_t bf = i < 30 ? gfull + (i & 3) * 8 : bar_last + (i & 1) * 8;
            mbar_wait(gempty + (i & 3) * 8, gph);
            mbar_expect_tx(bf, ps ? GST_BYTES : 2 * UNIT);
            const int kt = ps == 2 ? (((cj & 1) * 4 + ((i >> 1) & 3)) * 4 + (i >> 3)) * 2 + (i & 1) : (i + (ps ? 0 : b & 14)) & 15;
            tma3d_mc<true>(base + unit_of(wt, i & 3) + rank * UNIT, mw, 0, kt * 64, wch, bf);
            if (i == 16) mbar_wait(bar_cnt, 0);
            if (ps && i == 2) mbar_wait(bempty + 16, 1);
            if (ps) bulk_load_stream(base + unit_of(xt, i & 3), xs + kt * UNIT, UNIT, bf);
            PROF(ps == 2 && i >= 24, 40 + i - 24);
            if ((i & 3) == 3) gph ^= 1;
          }
          if (ps == 2) break;
          if (ps == 1) mbar_arrive(bar_go2);
          wch = ps ? ((wch >> 3) ^ rank) * 2 : wch + 4;
#pragma unroll 1
          for (int u = 0; u < 16; u++) {
            const bool isk = (u == 0) || ((u & 1) && u < 15);
            const int blk = (isk ? (u + 1) >> 1 : (u == 15 ? 7 : (u >> 1) - 1)) & 3;
            const uint32_t sl = base + unit_of(ps ? AT1 : AT0, u & 3), bf = bfull + (u & 3) * 8;
            if (u < 4) mbar_wait(gempty + ((u + 1) >> 1) * 8, gph);
            mbar_wait(bempty + (u & 3) * 8, ((u >> 2) & 1) ^ 1);
            mbar_expect_tx(bf, SLOT_BYTES);
            tma3d_mc<false>(sl + rank * 16384, isk ? &maps.k : &maps.v, 0, kvrow + blk * 128, rank, bf);
          }
        }
        if (b < NFFN) {
          mbar_wait(bar_ring0, 0);
#pragma unroll 1
          for (int u = 0; u < 12 + FPACE; u++) {
            if (u == E0) mbar_wait(bar_ring, 0);
            if (u >= FPACE) {
              mbar_wait(bar_box + (u - FPACE) * 8, 0);
              if (u - FPACE == 7) { mbar_arrive(bar_w1); PROF(true, 59); }
              if (u - FPACE == 11) { mbar_arrive(bar_w2); PROF(true, 60); }
            }
            if (u < 12) {
              mbar_expect_tx(bar_box + u * 8, UNIT);
              if (u < 8) tma2d(base + OFF_GATE + u * UNIT, u < 4 ? &maps.wg : &maps.wu, b * 32, (u & 3) * 256, bar_box + u * 8);
              else tma3d(base + (u - 8) * UNIT, &maps.wd, 0, b * 32, (u - 8) * 4, bar_box + u * 8);
            }
          }
        }
      }
    } else if (warp == 9) {
      if (lane == 0) {
        const uint32_t epoch = ld_relaxed(&g_epoch);
#pragma unroll 1
        for (int i = 0; i < 16; i++) {
          if (i == HDX) mbar_wait(bar_mod, 0);
          if (i == NRS) {
            wait_counter(&g_cnt_h[rb * 32], 8 * (epoch + 1));
            PROF(true, 26);
            fence_async();
            PROF(true, 15);
          }
          mbar_wait(xempty + (i & 3) * 8, ((i >> 2) & 1) ^ 1);
          mbar_expect_tx(xfull + (i & 3) * 8, UNIT);
          if (i < NRS) tma2d(base + (i & 3) * GST_BYTES, &maps.x, ((2 * cj + i) & 15) * 64, rb * 128, xfull + (i & 3) * 8);
          else bulk_load_stream(base + (i & 3) * GST_BYTES, g_h + (size_t)(rb * 16 + ((2 * cj + i) & 15)) * UNIT, UNIT, xfull + (i & 3) * 8);
        }
        prefetch_map(&maps.wo);
#pragma unroll 1
        for (int t = 0; t < 4; t++) {
#pragma unroll 1
          for (int w = 0; w < 2; w++) {
            mbar_wait(bar_ofull + w * 8, t & 1);
            uint8_t* dst = g_o + (size_t)(rb * 64 + (cj * 4 + t) * 2) * UNIT + w * 8192;
            bulk_store(dst, base + unit_of(QT, 2 * t) + w * 8192, 8192);
            bulk_store(dst + UNIT, base + unit_of(QT, 2 * t + 1) + w * 8192, 8192);
            asm volatile("cp.async.bulk.commit_group;" ::: "memory");
            asm volatile("cp.async.bulk.wait_group 0;" ::: "memory");
            mbar_arrive(bar_ofree + t * 8);
            fence_async();
            red_release(&g_cnt_o[((rb * 4 + t) * 2 + (cj >> 2)) * 32], 1);
          }
          if (t == PF2T) for (int u = 0; u < PF2; u++)
            tma3d_prefetch(&maps.wo, 0, ((((cj & 1) * 4 + (b >> 5)) * 4 + u) * 2 + ((b >> 4) & 1)) * 64, (cj ^ rank) * 2);
        }
        mbar_expect_tx(bar_xres, 32768);
        tma2d(base + OFF_RES, &maps.x, cj * 128, rb * 128, bar_xres);
        tma2d(base + OFF_RES + UNIT, &maps.x, cj * 128 + 64, rb * 128, bar_xres);
        wait_counter(&g_cnt_o[(rb * 8 + 4 + (cj & 1)) * 32], 8 * (epoch + 1));
        wait_counter(&g_cnt_o[(rb * 8 + 6 + (cj & 1)) * 32], 8 * (epoch + 1));
        fence_async();
        mbar_arrive(bar_cnt);
        PROF(true, 27);
      }
      __syncwarp();
      mbar_wait(bar_last, 0);
      bar_arrive(8, 160); bar_arrive(9, 160);
      mbar_wait(bar_last + 8, 0);
      bar_arrive(10, 160); bar_arrive(11, 160);
    } else {
      const int t2 = tid - 320;
      if (t2 == 0) {
        mbar_wait(bar_hpub, 0);
        PROF(true, 24);
        red_release(&g_cnt_h[rb * 32], 1);
        PROF(true, 25);
        prefetch_map(&maps.wg); prefetch_map(&maps.wu); prefetch_map(&maps.wd);
      }
      __syncwarp();
      if (b < NFFN) {
        mbar_wait(bar_go2, 0);
        const __nv_bfloat16* pg = ((b & 1) ? P.w_up : P.w_gate) + (b >> 1) * 64 + (size_t)t2 * FF;
        const __nv_bfloat16* pd = P.w_down + (size_t)b * 32768 + t2 * 64;
        PROF(t2 == 0, 13);
#pragma unroll 1
        for (int i = 0; i < WN; i += WB) {
          uint32_t v[WB];
#pragma unroll
          for (int u = 0; u < WB; u++)
            asm volatile("ld.global.cg.L2::128B.u32 %0, [%1];" : "=r"(v[u]) : "l"(i < 16 ? pg + (size_t)(i + u) * 64 * FF : pd + (i + u - 16) * 4096));
#pragma unroll
          for (int u = 1; u < WB; u++) v[0] ^= v[u];
          sts1(par + PAR_SINK + t2 * 4, v[0]);
        }
        PROF(t2 == 0, 14);
      }
      const uint32_t epoch = ld_relaxed(&g_epoch), tag = epoch % 3 + 1;
      mbar_wait(bar_xres, 0);
      float s1 = 0.f, s2 = 0.f;
#pragma unroll 1
      for (int q = 0; q < 4; q++) {
        const int col = q * 256 + t2 * 4;
        uint4 vsb = poll4(g_mod + 3 * DM + col, tag), vcb = poll4(g_mod + 4 * DM + col, tag);
        uint2 wr = *reinterpret_cast<const uint2*>(P.w_r + col);
        float c0 = rbf(1.f + bf_hi(vcb.x)), c1 = rbf(1.f + bf_hi(vcb.y)), c2 = rbf(1.f + bf_hi(vcb.z)), c3 = rbf(1.f + bf_hi(vcb.w));
        float a0 = c0 * bf_lo(wr.x), a1 = c1 * bf_hi(wr.x), a2 = c2 * bf_lo(wr.y), a3 = c3 * bf_hi(wr.y);
        s1 += (a0 + a1) + (a2 + a3);
        s2 += bf_hi(vsb.x) * bf_lo(wr.x) + bf_hi(vsb.y) * bf_hi(wr.x) + bf_hi(vsb.z) * bf_lo(wr.y) + bf_hi(vsb.w) * bf_hi(wr.y);
        if ((col >> 7) == cj) {
          const int lc = col & 127;
          uint4 vga = poll4(g_mod + 2 * DM + col, tag), vgb = poll4(g_mod + 5 * DM + col, tag);
          sts2(par + PAR_GA + lc * 2, __byte_perm(vga.x, vga.y, 0x7632), __byte_perm(vga.z, vga.w, 0x7632));
          sts2(par + PAR_GB + lc * 2, __byte_perm(vgb.x, vgb.y, 0x7632), __byte_perm(vgb.z, vgb.w, 0x7632));
          sts2(par + PAR_SB + lc * 2, __byte_perm(vsb.x, vsb.y, 0x7632), __byte_perm(vsb.z, vsb.w, 0x7632));
          sts2(par + PAR_CB1 + lc * 2, pack_bf(c0, c1), pack_bf(c2, c3));
          sts4(par + PAR_A + lc * 4, make_uint4(__float_as_uint(a0), __float_as_uint(a1), __float_as_uint(a2), __float_as_uint(a3)));
        }
      }
#pragma unroll
      for (int o = 16; o > 0; o >>= 1) { s1 += __shfl_xor_sync(0xffffffffu, s1, o); s2 += __shfl_xor_sync(0xffffffffu, s2, o); }
      if (lane == 0) sts2(par + PAR_CONST + (warp - 10) * 8, __float_as_uint(s1), __float_as_uint(s2));
      if (t2 < 2) {
        uint4 g = poll4(g_mod + 5 * DM + b * 8 + t2 * 4, tag);
        sts4(par + PAR_CONST + 16 + t2 * 16, g);
      }
      mbar_wait(bar_go, 0);
      for (int q = XR; q < XE; q++) st_b128(g_xch + ((size_t)b * 8 * 256 + q * 64 + t2) * 4, (epoch & 1) << 16, 0, 0, 0);
      for (int q = 0; q < 2; q++) st_relaxed4(g_stats + ((size_t)cj * SEQ + rb * 128 + q * 64 + t2) * 4, 0, 0, 0, 0);
      __threadfence();
      mbar_arrive(bar_par);
      mbar_wait(bar_ring, 0);
      if (b < NFFN)
        for (int q = 0; q < 4; q++) st_relaxed4(g_ypart + ((size_t)(q * 32 + (t2 >> 1)) * NFFN + b) * 8 + (t2 & 1) * 4, 0, 0, 0, 0);
      st_relaxed4(g_row + rb * 2 * DM + (t2 >> 5) * DM + cj * 128 + (t2 & 31) * 4, 0, 0, 0, 0);
      if (cj == 0 && t2 < 2) st_relaxed4(g_cand + rb * 8 + t2 * 4, 0, 0, 0, 0);
      __threadfence();
      mbar_arrive(bar_rst);
    }
    __syncwarp();
    cluster_arrive();
    cluster_wait();
  } else {
    const int wg = warp >> 2;

    uint32_t epoch, tag;
    {
      uint32_t* const pmod = g_modp + rank * 2 * DM + (b >> 1) * 32 + lane;
      uint32_t* const pln = g_ln1 + (rb * 128 + cj * 16 + warp) * 4;
      const uint32_t cv = ldg_nc1(P.c + rank * 512 + tid * 2);
      epoch = ld_relaxed(&g_epoch);
      if (warp == 0) st_relaxed(pmod, 0);
      if (lane == 0) { st_relaxed2(pln, 0, 0); st_relaxed2(pln + 32, 0, 0); }
      asm volatile("setmaxnreg.inc.sync.aligned.u32 232;");
      sts1(par + tid * 4, pack_bf(silu_f(bf_lo(cv)), silu_f(bf_hi(cv))));
      bar_sync(1, 320);
      tag = epoch % 3 + 1;
#pragma unroll
      for (int part = 0; part < 3; part++) {
        if (part != 1) {
          const uint32_t xa = base + (2 + part / 2) * GST_BYTES + warp * 2048 + lane * 16;
          mbar_wait(bar_hx + part * 4, 0);
          float s0 = 0.f, s1 = 0.f, q0 = 0.f, q1 = 0.f;
#pragma unroll
          for (int q = 0; q < 4; q++) {
            const uint4 xv = lds4(xa + q * 512);
            const uint32_t u[4] = {xv.x, xv.y, xv.z, xv.w};
#pragma unroll
            for (int e = 0; e < 4; e++) { const float lo = bf_lo(u[e]), hi = bf_hi(u[e]); s0 += lo; s1 += hi; q0 += lo * lo; q1 += hi * hi; }
          }
          s0 += s1; q0 += q1;
#pragma unroll
          for (int o = 16; o > 0; o >>= 1) { s0 += __shfl_xor_sync(0xffffffffu, s0, o); q0 += __shfl_xor_sync(0xffffffffu, q0, o); }
          const float mean = s0 * (1.f / DM);
          float mb, sd;
          ln_scalars(mean, fmaxf(q0 * (1.f / DM) - mean * mean, 0.f), mb, sd);
          if (lane == 0) st_relaxed2(pln + part * 16, __float_as_uint(mb) | tag, __float_as_uint(sd) | tag);
          PROF(tid == 0 && part == 2, 4);
        } else {
          float acc[8];
#pragma unroll
          for (int e = 0; e < 8; e++) acc[e] = 0.f;
          const uint32_t wa = stage + (tid >> 2) * 64 + (((tid ^ (tid >> 3)) & 3) << 4), sa = par + (tid >> 3) * 4, sh = (tid & 4) ? 0x3244 : 0x1044;
          mbar_wait(bar_hw, 0);
#pragma unroll
          for (int p = 0; p < 8; p++) {
            const uint4 w = lds4(wa + p * 4096);
            const float s = __uint_as_float(__byte_perm(lds1(sa + p * 128), 0, sh));
            acc[0] += s * bf_lo(w.x); acc[1] += s * bf_hi(w.x); acc[2] += s * bf_lo(w.y); acc[3] += s * bf_hi(w.y);
            acc[4] += s * bf_lo(w.z); acc[5] += s * bf_hi(w.z); acc[6] += s * bf_lo(w.w); acc[7] += s * bf_hi(w.w);
          }
#pragma unroll
          for (int e = 0; e < 4; e++) {
            const bool up = lane & 16;
            acc[e] = (up ? acc[e + 4] : acc[e]) + __shfl_xor_sync(0xffffffffu, up ? acc[e] : acc[e + 4], 16);
          }
#pragma unroll
          for (int e = 0; e < 2; e++) {
            const bool up = lane & 8;
            acc[e] = (up ? acc[e + 2] : acc[e]) + __shfl_xor_sync(0xffffffffu, up ? acc[e] : acc[e + 2], 8);
          }
          {
            const bool up = lane & 4;
            acc[0] = (up ? acc[1] : acc[0]) + __shfl_xor_sync(0xffffffffu, up ? acc[0] : acc[1], 4);
          }
          sts1(par + 1024 + warp * 128 + ((lane & 3) * 8 + (lane >> 2)) * 4, __float_as_uint(acc[0]));
          bar_sync(1, 256);
          if (warp == 0) {
            float s = 0.f;
#pragma unroll
            for (int w8 = 0; w8 < 8; w8++) s += __uint_as_float(lds1(par + 1024 + w8 * 128 + lane * 4));
            st_relaxed(pmod, (__float_as_uint(s) & ~3u) | tag);
          }
          PROF(tid == 0, 3);
        }
      }
      {
        uint2 s0 = ld_relaxed2(g_ln1 + (rb * 128 + (tid & 127)) * 4);
        uint4 v[4];
#pragma unroll
        for (int q = 0; q < 4; q++) v[q] = ld_relaxed4(g_modp + q * DM + tid * 4);
        {
          uint32_t n = 0;
          while (!(tag_ok(v[0], tag) && tag_ok(v[1], tag) && tag_ok(v[2], tag) && tag_ok(v[3], tag))) {
#pragma unroll
            for (int q = 0; q < 4; q++)
              if (!tag_ok(v[q], tag)) v[q] = ld_relaxed4(g_modp + q * DM + tid * 4);
            if (((s0.x ^ tag) | (s0.y ^ tag)) & 3u) s0 = ld_relaxed2(g_ln1 + (rb * 128 + (tid & 127)) * 4);
            watchdog(n);
          }
        }
        const uint32_t d = stage + (tid >> 2) * 64 + (tid & 1) * 32 + (tid & 2) * 2;
        sts1(d, pack_bf(1.f + rbf(untag_sum(v[1].x, v[3].x)), 1.f + rbf(untag_sum(v[1].y, v[3].y))));
        sts1(d + 16, pack_bf(1.f + rbf(untag_sum(v[1].z, v[3].z)), 1.f + rbf(untag_sum(v[1].w, v[3].w))));
        sts1(d + 8, pack_bf(untag_sum(v[0].x, v[2].x), untag_sum(v[0].y, v[2].y)));
        sts1(d + 24, pack_bf(untag_sum(v[0].z, v[2].z), untag_sum(v[0].w, v[2].w)));
        if (wg == 0) {
          uint32_t n = 0;
          while (((s0.x ^ tag) | (s0.y ^ tag)) & 3u) { s0 = ld_relaxed2(g_ln1 + (rb * 128 + tid) * 4); watchdog(n); }
          uint32_t ih, il;
          split_inv(bf_hi(s0.y), ih, il);
          sts4(stage + 4096 + tid * 16, make_uint4(__byte_perm(s0.x, 0, 0x3232), ih, il, 0));
        }
        mbar_arrive(bar_mod);
      }
      cluster_wait();
      if (wg == 1) bar_arrive(2, 256);
      mbar_wait(bar_mod, 0);
      PROF(tid == 0, 2);
    }

    const bool lane01 = lane < 2;
    uint32_t gph = 0;
    float f0 = 0.f, f1 = 0.f;
    const uint32_t rempty = mapa(bempty, lane & 1);
    const uint32_t rgempty = rempty + (gempty - bempty);
    float o[64], s[64];
#pragma unroll 1
    for (int ps = 0; ps < 3; ps++) {
      {
        const uint32_t xt = ps == 1 ? XT1 : XT2, wt = ps == 1 ? WT1 : WT2;
        const int nst = ps == 2 ? 28 : 16;
        if (ps == 0) {
          float ga[64], gb[64];
#pragma unroll
          for (int i = 0; i < 64; i++) { ga[i] = 0.f; gb[i] = 0.f; }
          uint32_t a[2][16];
          const uint32_t l = fresh_lane();
          const uint4 r0 = lds4(stage + 4096 + (warp * 16 + (l >> 2)) * 16), r1 = lds4(stage + 4096 + 128 + (warp * 16 + (l >> 2)) * 16);
          auto transform = [&](int i, uint32_t (&f)[16], uint32_t z) {
            const uint32_t ad = base + (i & 3) * GST_BYTES + wg * 8192 + frag_offset(warp) + z;
            mbar_wait(xfull + (i & 3) * 8, i >> 2);
#pragma unroll
            for (int kk = 0; kk < 4; kk++) ldmatrix4(ad ^ (kk * 32), f[4 * kk], f[4 * kk + 1], f[4 * kk + 2], f[4 * kk + 3]);
#pragma unroll
            for (int kk = 0; kk < 4; kk++) {
              const uint4 m = lds4(stage + (l & 3) * 16 + ((2 * cj + i) & 15) * 256 + kk * 64);
              f[4 * kk] = ln_mod(f[4 * kk], r0.x, r0.y, r0.z, m.x, m.z);
              f[4 * kk + 1] = ln_mod(f[4 * kk + 1], r1.x, r1.y, r1.z, m.x, m.z);
              f[4 * kk + 2] = ln_mod(f[4 * kk + 2], r0.x, r0.y, r0.z, m.y, m.w);
              f[4 * kk + 3] = ln_mod(f[4 * kk + 3], r1.x, r1.y, r1.z, m.y, m.w);
            }
            keep(f);
            mbar_arrive_pred(xempty + (i & 3) * 8, l == 0);
          };
          auto publish = [&](int u, uint32_t (&f)[16]) {
            const uint32_t sc = stage + 8192 + wg * 8192;
#pragma unroll
            for (int kk = 0; kk < 4; kk++) stmatrix4((sc + frag_offset(warp)) ^ (kk * 32), f[4 * kk], f[4 * kk + 1], f[4 * kk + 2], f[4 * kk + 3]);
            __syncwarp();
            const uint32_t src = sc + (warp & 3) * 2048 + l * 16;
            uint8_t* dst = g_h + (size_t)(rb * 16 + cj * 2 + u) * UNIT + warp * 2048 + l * 16;
#pragma unroll
            for (int p4 = 0; p4 < 4; p4++) stg4(dst + p4 * 512, lds4(src + p4 * 512));
            __syncwarp();
            if (u == 1) mbar_arrive_pred(bar_hpub, l == 0);
          };
          auto multiply = [&](int i, uint32_t (&f)[16]) {
            mbar_wait(gfull + (i & 3) * 8, i >> 2);
            const uint64_t db = make_desc(base + (i & 3) * GST_BYTES + UNIT, 8192, 1024);
            wg_fence();
#pragma unroll
            for (int kk = 0; kk < 4; kk++) mma256_rs(ga, gb, f[4 * kk], f[4 * kk + 1], f[4 * kk + 2], f[4 * kk + 3], db + kk * 128);
            wg_commit();
          };
          transform(0, a[0], 0); publish(0, a[0]); transform(1, a[1], 0); multiply(0, a[0]); publish(1, a[1]);
#pragma unroll
          for (int i = 1; i < NRS; i++) {
            if (i >= 2) {
              uint32_t z = r0.w;
#pragma unroll
              for (int k = 0; k < 16; k += 2) asm volatile("lop3.b32 %0, %1, %2, %0, 0xA8;" : "+r"(z) : "r"(a[i & 1][k]), "r"(a[i & 1][k + 1]));
              transform(i, a[i & 1], z);
            }
            multiply(i, a[i & 1]);
            wg_wait<1>();
            mbar_arrive_cl(rgempty + ((i + 3) & 3) * 8, lane01);
          }
          gph = (NRS >> 2) & 1;
          mbar_arrive_pred(bar_pread, lane == 0);
#pragma unroll 1
          for (int i = NRS; i < 16; i++) {
            mbar_wait(xfull + (i & 3) * 8, gph);
            mbar_wait(gfull + (i & 3) * 8, gph);
            const uint32_t xa = base + (i & 3) * GST_BYTES;
            const uint64_t da = make_desc(xa + wg * 8192, 16, 1024), db = make_desc(xa + UNIT, 8192, 1024);
            wg_fence();
#pragma unroll
            for (int kk = 0; kk < 4; kk++) mma256_ss(ga, gb, da + kk * 2, db + kk * 128, 1);
            wg_commit();
            wg_wait<1>();
            uint32_t z = r0.w;
#pragma unroll
            for (int k = 0; k < 16; k += 2) asm volatile("lop3.b32 %0, %1, %2, %0, 0xA8;" : "+r"(z) : "r"(a[1][k]), "r"(a[1][k + 1]));
            mbar_arrive_cl(rgempty + ((i + 3) & 3) * 8 + z, lane01);
            mbar_arrive_pred(xempty + ((i + 3) & 3) * 8, l == 0 && i != NRS);
            if ((i & 3) == 3) gph ^= 1;
          }
          wg_wait<0>();
          keep(ga); keep(gb);
#pragma unroll
          for (int i = 0; i < 64; i++) {
            asm volatile("mov.b32 %0, %1;" : "=f"(s[i]) : "f"(ga[i]));
            asm volatile("mov.b32 %0, %1;" : "=f"(o[i]) : "f"(gb[i]));
          }
        } else {
          float ga[64], gb[64];
#pragma unroll
          for (int i = 0; i < 64; i++) { ga[i] = 0.f; gb[i] = 0.f; }
#pragma unroll 1
          for (int i = 0; i < nst; i++) {
            mbar_wait(gfull + (i & 3) * 8, gph);
            const uint64_t da = make_desc(base + unit_of(xt, i & 3) + wg * 8192, 16, 1024), db = make_desc(base + unit_of(wt, i & 3), 8192, 1024);
            wg_fence();
#pragma unroll
            for (int kk = 0; kk < 4; kk++) mma256_ss(ga, gb, da + kk * 2, db + kk * 128, 1);
            wg_commit();
            wg_wait<1>();
            mbar_arrive_cl(rgempty + ((i + 3) & 3) * 8, lane01 && i != 0);
            if ((i & 3) == 3) gph ^= 1;
          }
          wg_wait<0>();
          keep(ga); keep(gb);
#pragma unroll
          for (int i = 0; i < 64; i++) {
            asm volatile("mov.b32 %0, %1;" : "=f"(s[i]) : "f"(ga[i]));
            asm volatile("mov.b32 %0, %1;" : "=f"(o[i]) : "f"(gb[i]));
          }
        }
        mbar_arrive_cl(rgempty + 24, lane01);
        if (ps == 2) break;
        mbar_wait(ps == 0 ? bar_pread : bar_ofree + 8, 0);
      }
      PROF(tid == 0, 8 + ps * 8);
      const uint32_t qw = base + wg * 8192, qt = QT >> (16 * ps), at = ps ? AT1 : AT0;
      store_chunk<0>(s, qw + unit_of(qt, 0) + frag_offset(warp));
      store_chunk<1>(s, qw + unit_of(qt, 1) + frag_offset(warp));
      fence_async_smem();
      mbar_wait(bfull, 0);
      bar_sync(2 + wg, 256);
      wg_fence();
      issue_qk(s, qw + unit_of(qt, 0), qw + unit_of(qt, 1), base + unit_of(at, 0));
      wg_commit();
      bar_arrive(3 - wg, 256);
      store_chunk<0>(o, qw + unit_of(qt, 2) + frag_offset(warp));
      store_chunk<1>(o, qw + unit_of(qt, 3) + frag_offset(warp));
      wg_wait<0>();
      keep(s);
      fence_async_smem();
      mbar_arrive_cl(rempty, lane01);
      float l0 = 0.f, l1 = 0.f;
      auto step = [&](auto odd_c, const int j, uint32_t (&pw)[32], uint32_t (&pr)[32]) {
        constexpr bool ODD = decltype(odd_c)::value;
        const bool first = !ODD && (j & 2) == 0, last = ODD && j == 7;
        float i0, i1, a0, a1;
        if (first) { i0 = inv_quad_sum(l0); i1 = inv_quad_sum(l1); l0 = 0.f; l1 = 0.f; }
        bool redo = !ODD && (j | ps) == 0;
        while (true) {
          if (redo) {
            float m0 = fmaxf(s[0], s[1]), m1 = fmaxf(s[2], s[3]);
#pragma unroll
            for (int i = 1; i < 16; i++) { m0 = fmaxf(m0, fmaxf(s[4 * i], s[4 * i + 1])); m1 = fmaxf(m1, fmaxf(s[4 * i + 2], s[4 * i + 3])); }
            m0 = fmaxf(m0, __shfl_xor_sync(0xffffffffu, m0, 1)); m1 = fmaxf(m1, __shfl_xor_sync(0xffffffffu, m1, 1));
            m0 = fmaxf(m0, __shfl_xor_sync(0xffffffffu, m0, 2)); m1 = fmaxf(m1, __shfl_xor_sync(0xffffffffu, m1, 2));
            m0 *= SCL2; m1 *= SCL2;
            if (!first) {
              m0 = fmaxf(m0, f0); m1 = fmaxf(m1, f1);
              const float c0 = ex2(f0 - m0), c1 = ex2(f1 - m1);
              l0 *= c0; l1 *= c1;
              wg_wait<0>();
              keep(o);
#pragma unroll
              for (int i = 0; i < 16; i++) { o[4 * i] *= c0; o[4 * i + 1] *= c0; o[4 * i + 2] *= c1; o[4 * i + 3] *= c1; }
            }
            f0 = m0; f1 = m1;
          }
          float b0 = 0.f, b1 = 0.f;
          a0 = 0.f; a1 = 0.f;
#pragma unroll
          for (int i = 0; i < 16; i++) {
            const float e0 = ex2(fmaf(s[4 * i], SCL2, -f0)), e1 = ex2(fmaf(s[4 * i + 1], SCL2, -f0));
            const float e2 = ex2(fmaf(s[4 * i + 2], SCL2, -f1)), e3 = ex2(fmaf(s[4 * i + 3], SCL2, -f1));
            a0 += e0; b0 += e1; a1 += e2; b1 += e3;
            pw[2 * i] = pack_bf(e0, e1); pw[2 * i + 1] = pack_bf(e2, e3);
          }
          a0 += b0; a1 += b1;
          if (redo) break;
          redo = __any_sync(0xffffffffu, !(a0 + a1 < 0x1p40f));
          if (first) {
            uint32_t m0 = __ballot_sync(0xffffffffu, a0 > 0x1p-40f), m1 = __ballot_sync(0xffffffffu, a1 > 0x1p-40f);
            m0 |= m0 >> 1; m1 |= m1 >> 1; m0 |= m0 >> 2; m1 |= m1 >> 2;
            redo = redo || (m0 & m1 & 0x11111111u) != 0x11111111u;
          }
          if (!redo) break;
        }
        l0 += a0; l1 += a1;
        const uint32_t ph = (j >> 1) & 1;
        mbar_wait(bfull + (ODD ? 24 : 8), ph);
        if (!last) mbar_wait(bfull + (ODD ? 0 : 16), ODD ? ph ^ 1 : ph);
        keep(pw);
        wg_wait<0>();
        keep(o);
        mbar_arrive_cl(rempty + (ODD ? 16 : 0), lane01 && (ODD || j));
        const bool so = !ODD && j == 4;
        if (so) store_chunk<0>(o, i0, i1, qw + unit_of(qt, 0) + frag_offset(warp));
        keep(o);
        bar_sync(2 + wg, 256);
        if (!last) {
          const uint32_t qn = qt >> (j >= 3 ? 8 : 0);
          wg_fence();
          issue_qk(s, qw + unit_of(qn, 0), qw + unit_of(qn, 1), base + unit_of(at, ODD ? 3 : 1));
          wg_commit();
        }
        if (so) { store_chunk<1>(o, i0, i1, qw + unit_of(qt, 1) + frag_offset(warp)); keep(o); }
        wg_fence();
        issue_pv(o, pw, base + unit_of(at, ODD ? (last ? 3 : 0) : 2), !first);
        wg_commit();
        bar_arrive(3 - wg, 256);
        if (so) { fence_async_smem(); mbar_arrive(bar_ofull + wg * 8); PROF(tid == 0, 9 + ps * 8); }
        wg_wait<1>();
        keep(s);
        mbar_arrive_cl(rempty + (ODD ? 24 : 8), lane01 && !last);
      };
      uint32_t pa[32], pb[32];
#pragma unroll 1
      for (int j = 0; j < 8; j += 2) {
        step(std::false_type{}, j, pa, pb);
        step(std::true_type{}, j + 1, pb, pa);
      }
      {
        const float i0 = inv_quad_sum(l0), i1 = inv_quad_sum(l1);
        wg_wait<0>();
        keep(o);
        mbar_arrive_cl(rempty + 24, lane01);
        store_chunk<0>(o, i0, i1, qw + unit_of(qt, 2) + frag_offset(warp));
        store_chunk<1>(o, i0, i1, qw + unit_of(qt, 3) + frag_offset(warp));
        fence_async_smem();
        mbar_arrive(bar_ofull + wg * 8);
      }
      PROF(tid == 0, 10 + ps * 8);
    }

    const int ln = fresh_lane(), g = ln >> 2, tq = ln & 3, ct = warp * 32 + ln;
    const bool lane0 = ln == 0;
    const int lrow0 = warp * 16 + g;
    const int grow0 = rb * 128 + lrow0;
    const uint32_t res = base + OFF_RES, trow = res + wg * 8192 + frag_offset(warp);
    uint32_t xr[32];
    {
      const uint64_t da = make_desc(base + wg * 8192, 16, 1024), db = make_desc(base, 8192, 1024);
      constexpr int U = UNIT / 16;
      constexpr int XU[4] = {6, 9, 12, 13}, WU[4] = {7, 10, 0, 2};
#define HALF_STAGE(acc, st, hf) _Pragma("unroll") for (int kk = 0; kk < 4; kk++) mma_ss<1>(acc, da + XU[st] * U + kk * 2, db + (WU[st] + hf) * U + kk * 128, 1)
      PROF(ct == 0, 19);
      mbar_wait(gfull, gph);
      mbar_wait(gfull + 8, gph);
      wg_fence();
      HALF_STAGE(o, 0, 1);
      HALF_STAGE(o, 1, 1);
      bar_sync(8 + wg, 160);
      HALF_STAGE(o, 2, 1);
      HALF_STAGE(s, 0, 0);
      bar_sync(10 + wg, 160);
      HALF_STAGE(o, 3, 1);
      wg_commit();
      HALF_STAGE(s, 1, 0);
      HALF_STAGE(s, 2, 0);
      wg_commit();
      wg_wait<1>();
      keep(o);
      mbar_arrive_pred(bar_ring0, lane0);
      PROF(ct == 0, 20);
      mbar_wait(bar_par, 0);
      uint32_t* xo = g_xch + ((size_t)b * 8 * 256 + ct) * 4;
      const uint32_t par1 = (~epoch & 1) << 16;
      uint32_t w[32];
      pack_p(o, w);
#pragma unroll
      for (int i = 0; i < 8; i++) w[4 * i] = (w[4 * i] & ~0x10000u) | par1;
      keep(w);
#pragma unroll
      for (int i = 0; i < 8; i++) st_b128(xo + i * 1024, w[4 * i], w[4 * i + 1], w[4 * i + 2], w[4 * i + 3]);
      wg_fence();
      HALF_STAGE(s, 3, 0);
      wg_commit();
      PROF(ct == 0, 21);
      const uint32_t* xi = g_xch + ((size_t)(b ^ 2) * 8 * 256 + ct) * 4;
      uint4 v[8];
      v[XF] = ld_b128(xi + XF * 1024);
      wg_wait<0>();
      keep(s);
      cluster_arrive();
      PROF(ct == 0, 23);
      uint32_t n = 0;
      while ((v[XF].x & 0x10000u) != par1) { v[XF] = ld_b128(xi + XF * 1024); watchdog(n); }
      PROF(ct == 0, 22);
      mbar_arrive_pred(bar_ring, lane0);
#pragma unroll
      for (int i = 0; i < 8; i++) if (i != XF) v[i] = ld_b128(xi + i * 1024);
      bool ok;
      do {
        ok = true;
#pragma unroll
        for (int i = 0; i < 8; i++)
          if (i != XF && (v[i].x & 0x10000u) != par1) { v[i] = ld_b128(xi + i * 1024); ok = false; }
        watchdog(n);
      } while (!ok);
#pragma unroll
      for (int i = 0; i < 8; i++) {
        s[8 * i] += bf_lo(v[i].x); s[8 * i + 1] += __uint_as_float(v[i].x & 0xfffe0000u); s[8 * i + 2] += bf_lo(v[i].y); s[8 * i + 3] += bf_hi(v[i].y);
        s[8 * i + 4] += bf_lo(v[i].z); s[8 * i + 5] += bf_hi(v[i].z); s[8 * i + 6] += bf_lo(v[i].w); s[8 * i + 7] += bf_hi(v[i].w);
      }
    }
    PROF(ct == 0, 28);
    mbar_wait(bar_xres, 0);
    float su0 = 0.f, su1 = 0.f, sq0 = 0.f, sq1 = 0.f, dt0 = 0.f, dt1 = 0.f;
#pragma unroll
    for (int i = 0; i < 16; i++) {
      if (!(i & 1)) {
        ldmatrix4((trow ^ ((i & 7) << 4)) + (i >> 3) * 16384, xr[2 * i], xr[2 * i + 1], xr[2 * i + 2], xr[2 * i + 3]);
      }
      const uint32_t ga = lds1(par + PAR_GA + (8 * i + 2 * tq) * 2);
      const uint2 av = lds2(par + PAR_A + (8 * i + 2 * tq) * 4);
      const uint32_t u0 = hadd2(xr[2 * i], hmul2(ga, pack_bf(s[4 * i], s[4 * i + 1])));
      const uint32_t u1 = hadd2(xr[2 * i + 1], hmul2(ga, pack_bf(s[4 * i + 2], s[4 * i + 3])));
      xr[2 * i] = u0; xr[2 * i + 1] = u1;
      const float a = bf_lo(u0), c = bf_hi(u0), d = bf_lo(u1), e = bf_hi(u1);
      su0 += a + c; su1 += d + e;
      sq0 += a * a + c * c; sq1 += d * d + e * e;
      dt0 += a * __uint_as_float(av.x) + c * __uint_as_float(av.y);
      dt1 += d * __uint_as_float(av.x) + e * __uint_as_float(av.y);
    }
#pragma unroll
    for (int o2 = 1; o2 < 4; o2 <<= 1) {
      su0 += __shfl_xor_sync(0xffffffffu, su0, o2); su1 += __shfl_xor_sync(0xffffffffu, su1, o2);
      sq0 += __shfl_xor_sync(0xffffffffu, sq0, o2); sq1 += __shfl_xor_sync(0xffffffffu, sq1, o2);
      dt0 += __shfl_xor_sync(0xffffffffu, dt0, o2); dt1 += __shfl_xor_sync(0xffffffffu, dt1, o2);
    }
    if (tq < 2) st_b128(g_stats + ((size_t)cj * SEQ + grow0 + tq * 8) * 4, __float_as_uint(tq ? su1 : su0), __float_as_uint(tq ? sq1 : sq0), __float_as_uint(tq ? dt1 : dt0), tag);
    PROF(ct == 0, 29);
#pragma unroll
    for (int i = 0; i < 16; i += 2) stmatrix4((trow ^ ((i & 7) << 4)) + (i >> 3) * 16384, xr[2 * i], xr[2 * i + 1], xr[2 * i + 2], xr[2 * i + 3]);
    {
      const uint32_t* sp = g_stats + ((size_t)(2 * tq) * SEQ + grow0) * 4;
      uint4 v0 = ld_b128(sp), v1 = ld_b128(sp + SEQ * 4), v2 = ld_b128(sp + 32), v3 = ld_b128(sp + SEQ * 4 + 32);
      uint32_t n = 0;
      while (v0.w != tag || v1.w != tag || v2.w != tag || v3.w != tag) {
        if (v0.w != tag) v0 = ld_b128(sp);
        if (v1.w != tag) v1 = ld_b128(sp + SEQ * 4);
        if (v2.w != tag) v2 = ld_b128(sp + 32);
        if (v3.w != tag) v3 = ld_b128(sp + SEQ * 4 + 32);
        watchdog(n);
      }
      su0 = __uint_as_float(v0.x) + __uint_as_float(v1.x); sq0 = __uint_as_float(v0.y) + __uint_as_float(v1.y); dt0 = __uint_as_float(v0.z) + __uint_as_float(v1.z);
      su1 = __uint_as_float(v2.x) + __uint_as_float(v3.x); sq1 = __uint_as_float(v2.y) + __uint_as_float(v3.y); dt1 = __uint_as_float(v2.z) + __uint_as_float(v3.z);
    }
#pragma unroll
    for (int o2 = 1; o2 < 4; o2 <<= 1) {
      su0 += __shfl_xor_sync(0xffffffffu, su0, o2); su1 += __shfl_xor_sync(0xffffffffu, su1, o2);
      sq0 += __shfl_xor_sync(0xffffffffu, sq0, o2); sq1 += __shfl_xor_sync(0xffffffffu, sq1, o2);
      dt0 += __shfl_xor_sync(0xffffffffu, dt0, o2); dt1 += __shfl_xor_sync(0xffffffffu, dt1, o2);
    }
    PROF(ct == 0, 30);
    float mb0, sd0, mb1, sd1;
    {
      const float m0 = su0 * (1.f / DM), m1 = su1 * (1.f / DM);
      ln_scalars(m0, fmaxf(sq0 * (1.f / DM) - m0 * m0, 0.f), mb0, sd0);
      ln_scalars(m1, fmaxf(sq1 * (1.f / DM) - m1 * m1, 0.f), mb1, sd1);
    }
    const float inv0 = 1.f / sd0, inv1 = 1.f / sd1;
    uint32_t ih0, il0, ih1, il1;
    split_inv(sd0, ih0, il0);
    split_inv(sd1, ih1, il1);
    const uint4 cst = lds4(par + PAR_CONST);
    const float A1 = __uint_as_float(cst.x) + __uint_as_float(cst.z), A2 = __uint_as_float(cst.y) + __uint_as_float(cst.w);
    const float r0 = (dt0 - mb0 * A1) * inv0 + A2, r1 = (dt1 - mb1 * A1) * inv1 + A2;
    float rbest = r1 > r0 ? r1 : r0;
    int ibest = r1 > r0 ? lrow0 + 8 : lrow0;
#pragma unroll
    for (int o2 = 4; o2 < 32; o2 <<= 1) {
      const float ro = __shfl_xor_sync(0xffffffffu, rbest, o2);
      const int io = __shfl_xor_sync(0xffffffffu, ibest, o2);
      if (ro > rbest || (ro == rbest && io < ibest)) { rbest = ro; ibest = io; }
    }
    if (lane0) sts2(par + PAR_RED + warp * 8, __float_as_uint(rbest), ibest);
    PROF(ct == 0, 38);
    mbar_wait(bar_rst, 0);
    bar_sync(1, 256);
    PROF(ct == 0, 39);
    {
      const uint2 cv = lds2(par + PAR_RED + (ln & 7) * 8);
      rbest = __uint_as_float(cv.x); ibest = cv.y;
#pragma unroll
      for (int o2 = 1; o2 < 8; o2 <<= 1) {
        const float ro = __shfl_xor_sync(0xffffffffu, rbest, o2);
        const int io = __shfl_xor_sync(0xffffffffu, ibest, o2);
        if (ro > rbest || (ro == rbest && io < ibest)) { rbest = ro; ibest = io; }
      }
    }
    if (cj == 0 && ct == 0) st_relaxed2(g_cand + rb * 8, tagf(rbest, tag), ((rb * 128 + ibest) << 2) | tag);
    const uint32_t mm0 = pack_bf(mb0, mb0), mm1 = pack_bf(mb1, mb1);
    if ((ibest >> 4) == warp) {
      const bool hi = ibest & 8;
      const int src = (ibest & 7) * 4, ch = g * 2;
      const uint32_t mm = __shfl_sync(0xffffffffu, hi ? mm1 : mm0, src), ih = __shfl_sync(0xffffffffu, hi ? ih1 : ih0, src), il = __shfl_sync(0xffffffffu, hi ? il1 : il0, src);
      const uint32_t xa = res + (ch >> 3) * 16384 + ibest * 128 + (((ch & 7) ^ (ibest & 7)) << 4) + tq * 4;
      const uint32_t x0 = lds1(xa), x1 = lds1(xa ^ 16);
      const uint32_t pc = par + (8 * ch + 2 * tq) * 2;
      const uint32_t h0 = ln_mod(x0, mm, ih, il, lds1(pc + PAR_CB1), lds1(pc + PAR_SB)), h1 = ln_mod(x1, mm, ih, il, lds1(pc + PAR_CB1 + 16), lds1(pc + PAR_SB + 16));
      uint32_t* dst = g_row + rb * 2 * DM + cj * 128 + ln * 4;
      st_pairs(dst, h0, h1, tag);
      st_pairs(dst + DM, x0, x1, tag);
      __syncwarp();
    }
    uint32_t wf[128];
    const uint32_t frow = (ln & 7) + (ln >> 4) * 8;
    const uint32_t wfa = base + OFF_GATE + warp * 8192 + frow * 64 + ((((ln >> 3) & 1) ^ ((frow >> 1) & 3)) << 4);
#define LOAD_WF(f) ldmatrix4t((wfa ^ (((f) & 1) * 32)) + (((f) >> 1) & 1) * 4 * UNIT + ((f) >> 2) * 1024, wf[4 * (f)], wf[4 * (f) + 1], wf[4 * (f) + 2], wf[4 * (f) + 3])
    const bool early = __all_sync(0xffffffffu, b >= NFFN || mbar_test(bar_w1, 0));
    PROF(ct == 0, 37);
#pragma unroll
    for (int i = 0; i < 16; i += 2) {
      uint32_t ov[4];
      if (early) {
#pragma unroll
        for (int mt = 0; mt < 4; mt++) LOAD_WF(i * 2 + mt);
      }
#pragma unroll
      for (int u = 0; u < 2; u++) {
        const int ii = i + u;
        const uint32_t cb1 = lds1(par + PAR_CB1 + (8 * ii + 2 * tq) * 2), sb = lds1(par + PAR_SB + (8 * ii + 2 * tq) * 2);
        const uint32_t gb = lds1(par + PAR_GB + (8 * ii + 2 * tq) * 2);
        const uint32_t h0 = ln_mod(xr[2 * ii], mm0, ih0, il0, cb1, sb), h1 = ln_mod(xr[2 * ii + 1], mm1, ih1, il1, cb1, sb);
        ov[2 * u] = hadd2(xr[2 * ii], hmul2(gb, h0));
        ov[2 * u + 1] = hadd2(xr[2 * ii + 1], hmul2(gb, h1));
      }
      stmatrix4((trow ^ ((i & 7) << 4)) + (i >> 3) * 16384, ov[0], ov[1], ov[2], ov[3]);
    }
    PROF(ct == 0, 31);
    auto store_tile = [&](int skip) {
      const int wrow0 = wg * 64 + (warp & 3) * 16;
#pragma unroll
      for (int p = 0; p < 8; p++) {
        const int row = 2 * p + (ln >> 4), ch = ln & 15;
        const uint4 v = lds4(res + (ch >> 3) * 16384 + (wrow0 + row) * 128 + (((ch & 7) ^ (row & 7)) << 4));
        if (rb * 128 + wrow0 + row != skip) *reinterpret_cast<uint4*>(P.out + (size_t)(rb * 128 + wrow0 + row) * DM + cj * 128 + ch * 8) = v;
      }
    };
    uint2 cv = ld_relaxed2(g_cand + (ln & 15) * 8);
    if (!early) {
      mbar_wait(bar_w1, 0);
#pragma unroll
      for (int f = 0; f < 32; f++) LOAD_WF(f);
    }
    float rwin; int iwin;
    uint4 hv[8];
    uint32_t wd[64];
    const uint32_t wda = base + warp * 8192 + frow * 128 + ((((ln >> 3) & 1) ^ (ln & 7)) << 4);
#define LOAD_WD(f) ldmatrix4t((wda ^ ((((f) >> 1) & 3) * 32)) + ((f) >> 3) * 4096 + ((f) & 1) * 2048, wd[4 * (f)], wd[4 * (f) + 1], wd[4 * (f) + 2], wd[4 * (f) + 3])
    {
      uint32_t n = 0;
      int cur = -1;
      while (true) {
        const bool valid = !(((cv.x ^ tag) | (cv.y ^ tag)) & 3u);
        const uint32_t bits = cv.x & ~3u;
        const uint32_t key = valid ? ((int)bits < 0 ? ~bits : bits | 0x80000000u) : 0u;
        const uint32_t best = __reduce_max_sync(0xffffffffu, key);
        const int src = (__ffs(__ballot_sync(0xffffffffu, key == best)) - 1) & 15;
        if (best && src != cur) {
          cur = src;
#pragma unroll
          for (int i = 0; i < 8; i++) hv[i] = ld_pairs(g_row + cur * 2 * DM + warp * 128 + i * 16 + tq * 4);
        }
        if (__all_sync(0xffffffffu, valid)) break;
        if (!valid) cv = ld_relaxed2(g_cand + (ln & 15) * 8);
        watchdog(n);
      }
      rwin = __uint_as_float(__shfl_sync(0xffffffffu, cv.x, cur) & ~3u);
      iwin = __shfl_sync(0xffffffffu, cv.y, cur) >> 2;
    }
    PROF(ct == 0, 32);
    const uint32_t* wrow = g_row + (iwin >> 7) * 2 * DM;
    if (b < NFFN) {
      {
        uint32_t n = 0;
        bool ok;
        do {
          ok = true;
#pragma unroll
          for (int i = 0; i < 8; i++)
            if (hv[i].y != tag || hv[i].w != tag) { hv[i] = ld_pairs(wrow + warp * 128 + i * 16 + tq * 4); ok = false; }
          watchdog(n);
        } while (!ok);
      }
      __syncwarp();
      PROF(ct == 0, 33);
      float d[8][4];
#pragma unroll
      for (int i = 0; i < 8; i++) { d[i][0] = 0.f; d[i][1] = 0.f; d[i][2] = 0.f; d[i][3] = 0.f; }
#pragma unroll
      for (int ks = 0; ks < 8; ks++) {
#pragma unroll
        for (int mt = 0; mt < 4; mt++) {
          const int r = ks * 16 + mt * 4;
          mma16816(d[mt + (ks & 1) * 4], wf[r], wf[r + 1], wf[r + 2], wf[r + 3], hv[ks].x, hv[ks].z);
        }
        if (ks == 1) mbar_wait(bar_w2, 0);
        if (ks >= 1) {
#pragma unroll
          for (int f = 4 * ks - 4; f < 16 && f < 4 * ks; f++) LOAD_WD(f);
        }
      }
      const uint32_t red = base + OFF_GATE;
      if (tq == 0) {
        const uint32_t dst = red + warp * 8192 + g * 32;
        sts4(dst, make_uint4(__float_as_uint(d[0][0] + d[4][0]), __float_as_uint(d[0][2] + d[4][2]), __float_as_uint(d[1][0] + d[5][0]), __float_as_uint(d[1][2] + d[5][2])));
        sts4(dst + 16, make_uint4(__float_as_uint(d[2][0] + d[6][0]), __float_as_uint(d[2][2] + d[6][2]), __float_as_uint(d[3][0] + d[7][0]), __float_as_uint(d[3][2] + d[7][2])));
      }
      bar_sync(1, 256);
      uint32_t ab[4];
      {
        float G = 0.f, U = 0.f;
        const uint32_t src = red + (ln & 7) * 32 + (ln >> 3) * 4;
#pragma unroll
        for (int w8 = 0; w8 < 8; w8++) { G += __uint_as_float(lds1(src + w8 * 8192)); U += __uint_as_float(lds1(src + w8 * 8192 + 16)); }
        const float act = rbf(silu_f(rbf(G))) * rbf(U);
        const uint32_t pk = pack_bf(act, __shfl_down_sync(0xffffffffu, act, 1));
#pragma unroll
        for (int i = 0; i < 4; i++) ab[i] = __shfl_sync(0xffffffffu, pk, i * 8 + tq * 2);
      }
      PROF(ct == 0, 34);
#pragma unroll
      for (int mt = 0; mt < 8; mt++) {
        d[mt][0] = 0.f; d[mt][1] = 0.f; d[mt][2] = 0.f; d[mt][3] = 0.f;
        mma16816(d[mt], wd[mt * 8], wd[mt * 8 + 1], wd[mt * 8 + 2], wd[mt * 8 + 3], ab[0], ab[1]);
        mma16816(d[mt], wd[mt * 8 + 4], wd[mt * 8 + 5], wd[mt * 8 + 6], wd[mt * 8 + 7], ab[2], ab[3]);
      }
#pragma unroll
      for (int i = 0; i < 4; i++) {
        const int m4 = (i >> 1) * 4, e = (i & 1) * 2;
        const float y = (tq & 2) ? ((tq & 1) ? d[m4 + 3][e] : d[m4 + 2][e]) : ((tq & 1) ? d[m4 + 1][e] : d[m4][e]);
        st_relaxed(g_ypart + ((size_t)(warp * 16 + (m4 + tq) * 2 + (i & 1)) * NFFN + b) * 8 + g, tagf(y, tag));
      }
      PROF(ct == 0, 35);
    }
    store_tile(iwin);
    {
      uint2 fh = make_uint2(0, 0), fx = make_uint2(0, 0);
      const uint32_t* src = wrow + (b >> 1) * 16 + (ct & 3) * 4 + (b & 1) * 2;
      if (ct < 4) { fh = ld_pair(src); fx = ld_pair(src + DM); }
      float y0 = 0.f, y1 = 0.f, y2 = 0.f, y3 = 0.f;
      if (ct < 2 * NFFN) {
        const uint4 v = poll4(g_ypart + (size_t)b * NFFN * 8 + ct * 4, tag);
        y0 = __uint_as_float(v.x & ~3u); y1 = __uint_as_float(v.y & ~3u); y2 = __uint_as_float(v.z & ~3u); y3 = __uint_as_float(v.w & ~3u);
      }
      __syncwarp();
      PROF(ct == 0, 5); PROF(ct == 96, 11); PROF(ct == 192, 12);
      if (ct < 4) {
        uint32_t n = 0;
        while (fh.y != tag || fx.y != tag) { fh = ld_pair(src); fx = ld_pair(src + DM); watchdog(n); }
      }
#pragma unroll
      for (int o2 = 2; o2 < 32; o2 <<= 1) {
        y0 += __shfl_xor_sync(0xffffffffu, y0, o2); y1 += __shfl_xor_sync(0xffffffffu, y1, o2);
        y2 += __shfl_xor_sync(0xffffffffu, y2, o2); y3 += __shfl_xor_sync(0xffffffffu, y3, o2);
      }
      if (ln < 2) sts4(par + PAR_RED + 64 + warp * 32 + ln * 16, make_uint4(__float_as_uint(y0), __float_as_uint(y1), __float_as_uint(y2), __float_as_uint(y3)));
      PROF(ct == 0, 6);
      bar_sync(1, 256);
      PROF(ct == 0, 7);
      if (ct < 4) {
        float ya = 0.f, yb = 0.f;
#pragma unroll
        for (int w8 = 0; w8 < 7; w8++) {
          const uint2 v = lds2(par + PAR_RED + 64 + w8 * 32 + ct * 8);
          ya += __uint_as_float(v.x); yb += __uint_as_float(v.y);
        }
        const float rs = rbf(1.f / (1.f + __expf(-rbf(rwin))));
        const uint2 gv = lds2(par + PAR_CONST + 16 + ct * 8);
        const uint32_t upd = hmul2(pack_bf(ya, yb), pack_bf(rs, rs));
        *reinterpret_cast<uint32_t*>(P.out + (size_t)iwin * DM + b * 8 + ct * 2) =
            hadd2(fx.x, hmul2(__byte_perm(gv.x, gv.y, 0x7632), hadd2(fh.x, upd)));
      }
      if (b == 0 && ct == 0) st_relaxed(&g_epoch, epoch + 1);
    }
    PROF(ct == 0, 36);
    cluster_wait();
  }
}

typedef CUresult (*EncodeFn)(CUtensorMap*, CUtensorMapDataType, cuuint32_t, void*, const cuuint64_t*, const cuuint64_t*,
                             const cuuint32_t*, const cuuint32_t*, CUtensorMapInterleave, CUtensorMapSwizzle,
                             CUtensorMapL2promotion, CUtensorMapFloatOOBfill);

void map2d(EncodeFn enc, CUtensorMap* m, const void* p, uint64_t rows, uint64_t cols, uint32_t brows) {
  cuuint64_t dims[2] = {cols, rows}, strides[1] = {cols * 2};
  cuuint32_t box[2] = {64, brows}, es[2] = {1, 1};
  enc(m, CU_TENSOR_MAP_DATA_TYPE_BFLOAT16, 2, const_cast<void*>(p), dims, strides, box, es, CU_TENSOR_MAP_INTERLEAVE_NONE,
      CU_TENSOR_MAP_SWIZZLE_128B, CU_TENSOR_MAP_L2_PROMOTION_L2_256B, CU_TENSOR_MAP_FLOAT_OOB_FILL_NONE);
}
void map2d_narrow(EncodeFn enc, CUtensorMap* m, const void* p, uint64_t rows, uint64_t cols) {
  cuuint64_t dims[2] = {cols, rows}, strides[1] = {cols * 2};
  cuuint32_t box[2] = {32, 256}, es[2] = {1, 1};
  enc(m, CU_TENSOR_MAP_DATA_TYPE_BFLOAT16, 2, const_cast<void*>(p), dims, strides, box, es, CU_TENSOR_MAP_INTERLEAVE_NONE,
      CU_TENSOR_MAP_SWIZZLE_64B, CU_TENSOR_MAP_L2_PROMOTION_L2_64B, CU_TENSOR_MAP_FLOAT_OOB_FILL_NONE);
}
void map3d(EncodeFn enc, CUtensorMap* m, const void* p, uint64_t rows, uint64_t cols, uint32_t brows, uint32_t nch) {
  cuuint64_t dims[3] = {64, rows, cols / 64}, strides[2] = {cols * 2, 128};
  cuuint32_t box[3] = {64, brows, nch}, es[3] = {1, 1, 1};
  enc(m, CU_TENSOR_MAP_DATA_TYPE_BFLOAT16, 3, const_cast<void*>(p), dims, strides, box, es, CU_TENSOR_MAP_INTERLEAVE_NONE,
      CU_TENSOR_MAP_SWIZZLE_128B, CU_TENSOR_MAP_L2_PROMOTION_L2_256B, CU_TENSOR_MAP_FLOAT_OOB_FILL_NONE);
}

}

extern "C" void kernel_launch(void* const* d_in, const int* in_sizes, int n_in, void* d_out, int out_size) {
  (void)in_sizes; (void)n_in; (void)out_size;
  static EncodeFn enc = nullptr;
  if (!enc) {
    void* fn = nullptr;
    cudaDriverEntryPointQueryResult st;
    cudaGetDriverEntryPoint("cuTensorMapEncodeTiled", &fn, cudaEnableDefault, &st);
    enc = (EncodeFn)fn;
    cudaFuncSetAttribute(fused_kernel, cudaFuncAttributeMaxDynamicSharedMemorySize, SMEM_BYTES);
  }
  Maps maps;
  map2d(enc, &maps.x, d_in[0], SEQ, DM, 128);
  map3d(enc, &maps.wq, d_in[3], DM, NQ, 64, 2);
  map3d(enc, &maps.k, d_in[1], 4 * SK, 128, 128, 1);
  map3d(enc, &maps.v, d_in[2], 4 * SK, 128, 128, 1);
  map3d(enc, &maps.wo, d_in[4], NQ, DM, 64, 2);
  map2d_narrow(enc, &maps.wg, d_in[7], DM, FF);
  map2d_narrow(enc, &maps.wu, d_in[8], DM, FF);
  map3d(enc, &maps.wd, d_in[9], FF, DM, 32, 4);
  map2d_narrow(enc, &maps.wm, d_in[11], DM, NMOD);
  Ptrs p;
  p.x = (const __nv_bfloat16*)d_in[0];
  p.w_r = (const __nv_bfloat16*)d_in[6];
  p.w_gate = (const __nv_bfloat16*)d_in[7];
  p.w_up = (const __nv_bfloat16*)d_in[8];
  p.w_down = (const __nv_bfloat16*)d_in[9];
  p.c = (const __nv_bfloat16*)d_in[10];
  p.w_mod = (const __nv_bfloat16*)d_in[11];
  p.out = (__nv_bfloat16*)d_out;
  fused_kernel<<<NMAIN + NHELP, 384, SMEM_BYTES>>>(maps, p);
}
```

```cpp
#include <cuda_runtime.h>
#include <cuda_bf16.h>
#include <cuda.h>
#include <stdint.h>
#include <type_traits>

#define HD 1
#define HDX 2
#define XF 4
#define XE 32
#define XR 16
#define PF2 2
#define PF2T 2
#define NRS 6
#define FPACE 2
#define GOST 24
#define WB 2
#define WN 16
#define VREL 7
#define E0 3

namespace {

constexpr int SEQ = 2048, DM = 1024, NQ = 4096, SK = 2048, WIN = 512, FF = 3584, NMOD = 6144;
constexpr int NMAIN = 128, NHELP = 4, NFFN = 112;
constexpr int NSLOT = 4, SLOT_BYTES = 32768, UNIT = 16384, GST_BYTES = 3 * UNIT;
constexpr uint32_t XT0 = 0x9630, XT1 = 0x54DC, XT2 = 0xDC96;
constexpr uint32_t WT0 = 0xA741, WT1 = 0x720A, WT2 = 0x20A7;
constexpr uint32_t AT0 = 0x7420, AT1 = 0x2C0A;
constexpr uint32_t QT = 0x549696DC;
constexpr int OFF_STAGE = 12 * UNIT;
constexpr int OFF_RES = 4 * UNIT, OFF_GATE = 6 * UNIT;
constexpr int OFF_PAR = 14 * UNIT;
constexpr int OFF_BAR = OFF_PAR + 2048 + 512;
constexpr int SMEM_BYTES = OFF_BAR + 512;
static_assert(SMEM_BYTES <= 232448, "smem");

constexpr int PAR_GA = 0, PAR_CB1 = 256, PAR_SB = 512, PAR_GB = 768;
constexpr int PAR_A = 1024;
constexpr int PAR_CONST = 1536;
constexpr int PAR_RED = 1600;
constexpr int PAR_SINK = 2176;

struct Maps {
  CUtensorMap x, wq, k, v, wo, wg, wu, wd, wm;
};
struct Ptrs {
  const __nv_bfloat16 *x, *w_r, *c, *w_mod, *w_gate, *w_up, *w_down;
  __nv_bfloat16* out;
};

__device__ __align__(1024) uint8_t g_act[16 * 80 * UNIT];
__device__ __align__(128) uint32_t g_mod[NMOD];
__device__ __align__(128) uint32_t g_modp[2 * 2 * DM];
__device__ __align__(128) uint32_t g_ln1[SEQ * 4];
__device__ __align__(128) uint32_t g_cnt_h[16 * 32];
__device__ __align__(128) uint32_t g_cnt_o[128 * 32];
__device__ __align__(128) uint32_t g_xch[NMAIN * 8 * 256 * 4];
__device__ __align__(128) uint32_t g_stats[8 * SEQ * 4];
__device__ __align__(128) uint32_t g_cand[16 * 8];
__device__ __align__(128) uint32_t g_row[16 * 2 * DM];
__device__ __align__(128) uint32_t g_ypart[NMAIN * NFFN * 8];
__device__ uint32_t g_epoch;

__device__ __forceinline__ uint32_t fresh_lane() { uint32_t l; asm volatile("mov.u32 %0, %%laneid;" : "=r"(l)); return l; }
__device__ __forceinline__ uint32_t frag_offset(int warp) {
  const uint32_t l = fresh_lane();
  return ((warp & 3) * 16 + (l & 15)) * 128 + (((l >> 4) ^ (l & 7)) << 4);
}
__device__ __forceinline__ uint32_t smem_u32(const void* p) { return (uint32_t)__cvta_generic_to_shared(p); }
__device__ __forceinline__ void mbar_init(uint32_t bar, uint32_t cnt) {
  asm volatile("mbarrier.init.shared::cta.b64 [%0], %1;" ::"r"(bar), "r"(cnt) : "memory");
}
__device__ __forceinline__ void mbar_expect_tx(uint32_t bar, uint32_t bytes) {
  asm volatile("mbarrier.arrive.expect_tx.shared::cta.b64 _, [%0], %1;" ::"r"(bar), "r"(bytes) : "memory");
}
__device__ __forceinline__ void mbar_arrive(uint32_t bar) {
  asm volatile("mbarrier.arrive.shared::cta.b64 _, [%0];" ::"r"(bar) : "memory");
}
__device__ __forceinline__ void mbar_arrive_pred(uint32_t bar, bool p) {
  asm volatile("{ .reg .pred p; setp.ne.b32 p, %1, 0; @p mbarrier.arrive.shared::cta.b64 _, [%0]; }" ::"r"(bar), "r"((int)p) : "memory");
}
__device__ __forceinline__ void mbar_arrive_cl(uint32_t bar, uint32_t off, bool p = true) {
  asm volatile("{ .reg .pred p, q; .reg .b32 a; setp.ne.b32 q, %2, 0; setp.ne.and.b32 p, %0, 0, q; add.u32 a, %0, %1; @p mbarrier.arrive.shared::cluster.b64 _, [a]; }"
               ::"r"(bar), "r"(off), "r"((int)p) : "memory");
}
__device__ __forceinline__ uint32_t mapa(uint32_t addr, uint32_t cta) {
  uint32_t r; asm("mapa.shared::cluster.u32 %0, %1, %2;" : "=r"(r) : "r"(addr), "r"(cta)); return r;
}
__device__ __forceinline__ void cluster_arrive() { asm volatile("barrier.cluster.arrive.relaxed.aligned;" ::: "memory"); }
__device__ __forceinline__ void cluster_wait() { asm volatile("barrier.cluster.wait.aligned;" ::: "memory"); }
__device__ __forceinline__ void watchdog(uint32_t& n) {
  asm volatile("{\n.reg .pred q;\n.reg .u64 z;\nadd.u32 %0, %0, 1;\nsetp.gt.u32 q, %0, 0x1000000;\nmov.u64 z, 0;\n@q st.global.u32 [z], %0;\n}" : "+r"(n)::"memory");
}
__device__ __forceinline__ void mbar_wait(uint32_t bar, uint32_t parity) {
  asm volatile(
      "{\n.reg .pred p, q;\n.reg .u32 n;\n.reg .u64 z;\nmov.u32 n, 0;\nmov.u64 z, 0;\n"
      "WAIT_%=:\n"
      "mbarrier.try_wait.parity.shared::cta.b64 p, [%0], %1;\n"
      "@p bra DONE_%=;\n"
      "add.u32 n, n, 1;\n"
      "setp.gt.u32 q, n, 0x400000;\n"
      "@q st.global.u32 [z], n;\n"
      "bra WAIT_%=;\n"
      "DONE_%=:\n}" ::"r"(bar), "r"(parity) : "memory");
}
__device__ __forceinline__ bool mbar_test(uint32_t bar, uint32_t parity) {
  uint32_t ok;
  asm volatile("{\n.reg .pred p;\nmbarrier.test_wait.parity.shared::cta.b64 p, [%1], %2;\nselp.u32 %0, 1, 0, p;\n}" : "=r"(ok) : "r"(bar), "r"(parity) : "memory");
  return ok;
}
__device__ __forceinline__ uint64_t l2_stream() {
  uint64_t f; asm("createpolicy.fractional.L2::evict_first.b64 %0, 1.0;" : "=l"(f)); return f;
}
__device__ __forceinline__ void tma2d(uint32_t dst, const CUtensorMap* m, int c0, int c1, uint32_t bar) {
  asm volatile("cp.async.bulk.tensor.2d.shared::cluster.global.mbarrier::complete_tx::bytes.L2::cache_hint [%0], [%1, {%3, %4}], [%2], %5;"
               ::"r"(dst), "l"(m), "r"(bar), "r"(c0), "r"(c1), "l"(l2_stream()) : "memory");
}
__device__ __forceinline__ void tma3d_prefetch(const CUtensorMap* m, int c0, int c1, int c2) {
  asm volatile("cp.async.bulk.prefetch.tensor.3d.L2.global.tile [%0, {%1, %2, %3}];" ::"l"(m), "r"(c0), "r"(c1), "r"(c2) : "memory");
}
__device__ __forceinline__ void bulk_load(uint32_t dst, const void* src, uint32_t bytes, uint32_t bar) {
  asm volatile("cp.async.bulk.shared::cluster.global.mbarrier::complete_tx::bytes [%0], [%1], %2, [%3];" ::"r"(dst), "l"(src), "r"(bytes), "r"(bar) : "memory");
}
__device__ __forceinline__ void bulk_load_stream(uint32_t dst, const void* src, uint32_t bytes, uint32_t bar) {
  asm volatile("cp.async.bulk.shared::cluster.global.mbarrier::complete_tx::bytes.L2::cache_hint [%0], [%1], %2, [%3], %4;"
               ::"r"(dst), "l"(src), "r"(bytes), "r"(bar), "l"(l2_stream()) : "memory");
}
__device__ __forceinline__ void bulk_store(void* dst, uint32_t src, uint32_t bytes) {
  asm volatile("cp.async.bulk.global.shared::cta.bulk_group [%0], [%1], %2;" ::"l"(dst), "r"(src), "r"(bytes) : "memory");
}
__device__ __forceinline__ uint32_t unit_of(uint32_t table, uint32_t i) { return ((table >> (i * 4)) & 15) * UNIT; }
__device__ __forceinline__ void tma3d(uint32_t dst, const CUtensorMap* m, int c0, int c1, int c2, uint32_t bar) {
  asm volatile("cp.async.bulk.tensor.3d.shared::cluster.global.mbarrier::complete_tx::bytes.L2::cache_hint [%0], [%1, {%3, %4, %5}], [%2], %6;"
               ::"r"(dst), "l"(m), "r"(bar), "r"(c0), "r"(c1), "r"(c2), "l"(l2_stream()) : "memory");
}
template <bool STREAM>
__device__ __forceinline__ void tma3d_mc(uint32_t dst, const CUtensorMap* m, int c0, int c1, int c2, uint32_t bar) {
  if (STREAM)
    asm volatile("cp.async.bulk.tensor.3d.shared::cluster.global.mbarrier::complete_tx::bytes.multicast::cluster.L2::cache_hint [%0], [%1, {%3, %4, %5}], [%2], %6, %7;"
                 ::"r"(dst), "l"(m), "r"(bar), "r"(c0), "r"(c1), "r"(c2), "h"((uint16_t)3), "l"(l2_stream()) : "memory");
  else
    asm volatile("cp.async.bulk.tensor.3d.shared::cluster.global.mbarrier::complete_tx::bytes.multicast::cluster [%0], [%1, {%3, %4, %5}], [%2], %6;"
                 ::"r"(dst), "l"(m), "r"(bar), "r"(c0), "r"(c1), "r"(c2), "h"((uint16_t)3) : "memory");
}
__device__ __forceinline__ void prefetch_map(const CUtensorMap* m) {
  asm volatile("prefetch.tensormap [%0];" ::"l"(m) : "memory");
}
__device__ __forceinline__ void fence_async() { asm volatile("fence.proxy.async.global;" ::: "memory"); }
__device__ __forceinline__ void fence_async_smem() { asm volatile("fence.proxy.async.shared::cta;" ::: "memory"); }
__device__ __forceinline__ void bar_sync(int id, int n) { asm volatile("bar.sync %0, %1;" ::"r"(id), "r"(n) : "memory"); }
__device__ __forceinline__ void bar_arrive(int id, int n) { asm volatile("bar.arrive %0, %1;" ::"r"(id), "r"(n) : "memory"); }
__device__ __forceinline__ void wg_fence() { asm volatile("wgmma.fence.sync.aligned;" ::: "memory"); }
__device__ __forceinline__ void wg_commit() { asm volatile("wgmma.commit_group.sync.aligned;" ::: "memory"); }
template <int N> __device__ __forceinline__ void wg_wait() { asm volatile("wgmma.wait_group.sync.aligned %0;" ::"n"(N) : "memory"); }
__device__ __forceinline__ uint64_t make_desc(uint32_t addr, uint32_t lbo, uint32_t sbo) {
  return (uint64_t)((addr & 0x3FFFF) >> 4) | ((uint64_t)(lbo >> 4) << 16) | ((uint64_t)(sbo >> 4) << 32) | (1ull << 62);
}
__device__ __forceinline__ uint32_t ld_relaxed(const uint32_t* p) {
  uint32_t v; asm volatile("ld.relaxed.gpu.global.u32 %0, [%1];" : "=r"(v) : "l"(p) : "memory"); return v;
}
__device__ __forceinline__ uint32_t ld_acquire(const uint32_t* p) {
  uint32_t v; asm volatile("ld.acquire.gpu.global.u32 %0, [%1];" : "=r"(v) : "l"(p) : "memory"); return v;
}
__device__ __forceinline__ uint4 ld_relaxed4(const uint32_t* p) {
  uint4 v; asm volatile("ld.relaxed.gpu.global.v4.u32 {%0,%1,%2,%3}, [%4];" : "=r"(v.x), "=r"(v.y), "=r"(v.z), "=r"(v.w) : "l"(p) : "memory"); return v;
}
__device__ __forceinline__ uint2 ld_relaxed2(const uint32_t* p) {
  uint2 v; asm volatile("ld.relaxed.gpu.global.v2.u32 {%0,%1}, [%2];" : "=r"(v.x), "=r"(v.y) : "l"(p) : "memory"); return v;
}
__device__ __forceinline__ void st_relaxed(uint32_t* p, uint32_t v) {
  asm volatile("st.relaxed.gpu.global.u32 [%0], %1;" ::"l"(p), "r"(v) : "memory");
}
__device__ __forceinline__ void st_relaxed2(uint32_t* p, uint32_t a, uint32_t b) {
  asm volatile("st.relaxed.gpu.global.v2.u32 [%0], {%1,%2};" ::"l"(p), "r"(a), "r"(b) : "memory");
}
__device__ __forceinline__ void st_relaxed4(uint32_t* p, uint32_t a, uint32_t b, uint32_t c, uint32_t d) {
  asm volatile("st.relaxed.gpu.global.v4.u32 [%0], {%1,%2,%3,%4};" ::"l"(p), "r"(a), "r"(b), "r"(c), "r"(d) : "memory");
}
__device__ __forceinline__ void st_b128(uint32_t* p, uint32_t a, uint32_t b, uint32_t c, uint32_t d) {
  asm volatile("{ .reg .b64 u, v; .reg .b128 w; mov.b64 u, {%1, %2}; mov.b64 v, {%3, %4}; mov.b128 w, {u, v}; st.relaxed.gpu.global.b128 [%0], w; }"
               ::"l"(p), "r"(a), "r"(b), "r"(c), "r"(d) : "memory");
}
__device__ __forceinline__ uint4 ld_b128(const uint32_t* p) {
  uint4 r;
  asm volatile("{ .reg .b64 u, v; .reg .b128 w; ld.relaxed.gpu.global.b128 w, [%4]; mov.b128 {u, v}, w; mov.b64 {%0, %1}, u; mov.b64 {%2, %3}, v; }"
               : "=r"(r.x), "=r"(r.y), "=r"(r.z), "=r"(r.w) : "l"(p) : "memory");
  return r;
}
__device__ __forceinline__ void st_pairs(uint32_t* p, uint32_t a, uint32_t b, uint32_t tag) {
  asm volatile("{ .reg .b64 u, v; mov.b64 u, {%1, %3}; mov.b64 v, {%2, %3}; st.relaxed.gpu.global.v2.b64 [%0], {u, v}; }"
               ::"l"(p), "r"(a), "r"(b), "r"(tag) : "memory");
}
__device__ __forceinline__ uint4 ld_pairs(const uint32_t* p) {
  uint4 v;
  asm volatile("{ .reg .b64 u, v; ld.relaxed.gpu.global.v2.b64 {u, v}, [%4]; mov.b64 {%0, %1}, u; mov.b64 {%2, %3}, v; }"
               : "=r"(v.x), "=r"(v.y), "=r"(v.z), "=r"(v.w) : "l"(p) : "memory");
  return v;
}
__device__ __forceinline__ uint2 ld_pair(const uint32_t* p) {
  uint2 v;
  asm volatile("{ .reg .b64 u; ld.relaxed.gpu.global.b64 u, [%2]; mov.b64 {%0, %1}, u; }" : "=r"(v.x), "=r"(v.y) : "l"(p) : "memory");
  return v;
}
__device__ __forceinline__ void red_release(uint32_t* p, uint32_t v) {
  asm volatile("red.release.gpu.global.add.u32 [%0], %1;" ::"l"(p), "r"(v) : "memory");
}
__device__ __forceinline__ uint32_t ldg_nc1(const void* p) {
  uint32_t v;
  asm volatile("ld.global.nc.u32 %0, [%1];" : "=r"(v) : "l"(p));
  return v;
}
__device__ __forceinline__ uint4 ldg_nc4(const void* p) {
  uint4 v; asm volatile("ld.global.nc.L1::no_allocate.v4.u32 {%0,%1,%2,%3}, [%4];" : "=r"(v.x), "=r"(v.y), "=r"(v.z), "=r"(v.w) : "l"(p)); return v;
}
__device__ __forceinline__ void stg4(void* p, uint4 v) {
  asm volatile("st.global.v4.u32 [%0], {%1,%2,%3,%4};" ::"l"(p), "r"(v.x), "r"(v.y), "r"(v.z), "r"(v.w) : "memory");
}
__device__ __forceinline__ void wait_counter(const uint32_t* p, uint32_t target) {
  uint32_t n = 0;
  while ((int)(ld_acquire(p) - target) < 0) { watchdog(n); }
}
__device__ __forceinline__ uint32_t tagf(float v, uint32_t tag) { return (__float_as_uint(v) & ~3u) | tag; }
__device__ __forceinline__ bool tag_ok(uint4 v, uint32_t tag) { return (((v.x ^ tag) | (v.y ^ tag) | (v.z ^ tag) | (v.w ^ tag)) & 3u) == 0; }
__device__ __forceinline__ float untag_sum(uint32_t a, uint32_t b) { return __uint_as_float(a & ~3u) + __uint_as_float(b & ~3u); }
__device__ __forceinline__ uint4 poll4(const uint32_t* p, uint32_t tag) {
  uint4 v = ld_relaxed4(p);
  uint32_t n = 0;
  while (!tag_ok(v, tag)) { v = ld_relaxed4(p); watchdog(n); }
  return v;
}
__device__ __forceinline__ float bf_lo(uint32_t v) { return __uint_as_float(v << 16); }
__device__ __forceinline__ float bf_hi(uint32_t v) { return __uint_as_float(v & 0xffff0000u); }
__device__ __forceinline__ uint32_t pack_bf(float lo, float hi) {
  uint32_t r; asm("cvt.rn.bf16x2.f32 %0, %1, %2;" : "=r"(r) : "f"(hi), "f"(lo)); return r;
}
__device__ __forceinline__ float rbf(float v) { return __uint_as_float(pack_bf(0.f, v) & 0xffff0000u); }
__device__ __forceinline__ uint32_t hmul2(uint32_t a, uint32_t b) {
  uint32_t r; asm("mul.rn.bf16x2 %0, %1, %2;" : "=r"(r) : "r"(a), "r"(b)); return r;
}
__device__ __forceinline__ uint32_t hadd2(uint32_t a, uint32_t b) {
  uint32_t r; asm("add.rn.bf16x2 %0, %1, %2;" : "=r"(r) : "r"(a), "r"(b)); return r;
}
__device__ __forceinline__ uint32_t hsub2(uint32_t a, uint32_t b) {
  uint32_t r; asm("sub.rn.bf16x2 %0, %1, %2;" : "=r"(r) : "r"(a), "r"(b)); return r;
}
__device__ __forceinline__ uint32_t hmax2(uint32_t a, uint32_t b) {
  uint32_t r; asm("max.bf16x2 %0, %1, %2;" : "=r"(r) : "r"(a), "r"(b)); return r;
}
__device__ __forceinline__ float ex2(float x) { float r; asm("ex2.approx.ftz.f32 %0, %1;" : "=f"(r) : "f"(x)); return r; }
__device__ __forceinline__ void stmatrix4(uint32_t addr, uint32_t a, uint32_t b, uint32_t c, uint32_t d) {
  asm volatile("stmatrix.sync.aligned.m8n8.x4.shared.b16 [%0], {%1,%2,%3,%4};" ::"r"(addr), "r"(a), "r"(b), "r"(c), "r"(d) : "memory");
}
__device__ __forceinline__ void ldmatrix4(uint32_t addr, uint32_t& a, uint32_t& b, uint32_t& c, uint32_t& d) {
  asm volatile("ldmatrix.sync.aligned.m8n8.x4.shared.b16 {%0,%1,%2,%3}, [%4];" : "=r"(a), "=r"(b), "=r"(c), "=r"(d) : "r"(addr) : "memory");
}
__device__ __forceinline__ void ldmatrix4t(uint32_t addr, uint32_t& a, uint32_t& b, uint32_t& c, uint32_t& d) {
  asm volatile("ldmatrix.sync.aligned.m8n8.x4.trans.shared.b16 {%0,%1,%2,%3}, [%4];" : "=r"(a), "=r"(b), "=r"(c), "=r"(d) : "r"(addr) : "memory");
}
__device__ __forceinline__ void mma16816(float (&d)[4], uint32_t a0, uint32_t a1, uint32_t a2, uint32_t a3, uint32_t b0, uint32_t b1) {
  asm volatile("mma.sync.aligned.m16n8k16.row.col.f32.bf16.bf16.f32 {%0,%1,%2,%3}, {%4,%5,%6,%7}, {%8,%9}, {%0,%1,%2,%3};"
               : "+f"(d[0]), "+f"(d[1]), "+f"(d[2]), "+f"(d[3]) : "r"(a0), "r"(a1), "r"(a2), "r"(a3), "r"(b0), "r"(b1));
}
__device__ __forceinline__ void sts1(uint32_t a, uint32_t v) { asm volatile("st.shared.u32 [%0], %1;" ::"r"(a), "r"(v) : "memory"); }
__device__ __forceinline__ uint4 lds4(uint32_t a) {
  uint4 v; asm volatile("ld.shared.v4.u32 {%0,%1,%2,%3}, [%4];" : "=r"(v.x), "=r"(v.y), "=r"(v.z), "=r"(v.w) : "r"(a) : "memory"); return v;
}
__device__ __forceinline__ uint2 lds2(uint32_t a) {
  uint2 v; asm volatile("ld.shared.v2.u32 {%0,%1}, [%2];" : "=r"(v.x), "=r"(v.y) : "r"(a) : "memory"); return v;
}
__device__ __forceinline__ uint32_t lds1(uint32_t a) {
  uint32_t v; asm volatile("ld.shared.u32 %0, [%1];" : "=r"(v) : "r"(a) : "memory"); return v;
}
__device__ __forceinline__ void sts2(uint32_t a, uint32_t x, uint32_t y) { asm volatile("st.shared.v2.u32 [%0], {%1,%2};" ::"r"(a), "r"(x), "r"(y) : "memory"); }
__device__ __forceinline__ void sts4(uint32_t a, uint4 v) {
  asm volatile("st.shared.v4.u32 [%0], {%1,%2,%3,%4};" ::"r"(a), "r"(v.x), "r"(v.y), "r"(v.z), "r"(v.w) : "memory");
}
__device__ __forceinline__ float silu_f(float v) { return __fdividef(v, 1.f + __expf(-v)); }
__device__ __forceinline__ uint32_t hfma2(uint32_t a, uint32_t b, uint32_t c) {
  uint32_t r; asm("fma.rn.bf16x2 %0, %1, %2, %3;" : "=r"(r) : "r"(a), "r"(b), "r"(c)); return r;
}
__device__ __forceinline__ void split_inv(float sd, uint32_t& ih, uint32_t& il) {
  const float inv = 1.f / sd;
  ih = pack_bf(inv, inv);
  const float lo = inv - bf_lo(ih);
  il = pack_bf(lo, lo);
}
__device__ __forceinline__ uint32_t ln_mod(uint32_t x, uint32_t mean2, uint32_t ih, uint32_t il, uint32_t c1, uint32_t sh) {
  const uint32_t d = hsub2(x, mean2);
  return hadd2(hmul2(hfma2(d, ih, hmul2(d, il)), c1), sh);
}

#define R8(a, i) "+f"(a[i]), "+f"(a[i + 1]), "+f"(a[i + 2]), "+f"(a[i + 3]), "+f"(a[i + 4]), "+f"(a[i + 5]), "+f"(a[i + 6]), "+f"(a[i + 7])
#define D64 "{%0,%1,%2,%3,%4,%5,%6,%7,%8,%9,%10,%11,%12,%13,%14,%15,%16,%17,%18,%19,%20,%21,%22,%23,%24,%25,%26,%27,%28,%29,%30,%31," \
            "%32,%33,%34,%35,%36,%37,%38,%39,%40,%41,%42,%43,%44,%45,%46,%47,%48,%49,%50,%51,%52,%53,%54,%55,%56,%57,%58,%59,%60,%61,%62,%63}"
template <int TB>
__device__ __forceinline__ void mma_ss(float (&d)[64], uint64_t da, uint64_t db, int sc) {
  asm volatile("{\n.reg .pred p;\nsetp.ne.b32 p, %66, 0;\n"
               "wgmma.mma_async.sync.aligned.m64n128k16.f32.bf16.bf16 " D64 ", %64, %65, p, 1, 1, 0, %67;\n}"
               : R8(d, 0), R8(d, 8), R8(d, 16), R8(d, 24), R8(d, 32), R8(d, 40), R8(d, 48), R8(d, 56)
               : "l"(da), "l"(db), "r"(sc), "n"(TB));
}
template <int TB>
__device__ __forceinline__ void mma_rs(float (&d)[64], uint32_t a0, uint32_t a1, uint32_t a2, uint32_t a3, uint64_t db, int sc) {
  asm volatile("{\n.reg .pred p;\nsetp.ne.b32 p, %69, 0;\n"
               "wgmma.mma_async.sync.aligned.m64n128k16.f32.bf16.bf16 " D64 ", {%64,%65,%66,%67}, %68, p, 1, 1, %70;\n}"
               : R8(d, 0), R8(d, 8), R8(d, 16), R8(d, 24), R8(d, 32), R8(d, 40), R8(d, 48), R8(d, 56)
               : "r"(a0), "r"(a1), "r"(a2), "r"(a3), "l"(db), "r"(sc), "n"(TB));
}
#define D128 "{%0,%1,%2,%3,%4,%5,%6,%7,%8,%9,%10,%11,%12,%13,%14,%15,%16,%17,%18,%19,%20,%21,%22,%23,%24,%25,%26,%27,%28,%29,%30,%31," \
             "%32,%33,%34,%35,%36,%37,%38,%39,%40,%41,%42,%43,%44,%45,%46,%47,%48,%49,%50,%51,%52,%53,%54,%55,%56,%57,%58,%59,%60,%61,%62,%63," \
             "%64,%65,%66,%67,%68,%69,%70,%71,%72,%73,%74,%75,%76,%77,%78,%79,%80,%81,%82,%83,%84,%85,%86,%87,%88,%89,%90,%91,%92,%93,%94,%95," \
             "%96,%97,%98,%99,%100,%101,%102,%103,%104,%105,%106,%107,%108,%109,%110,%111,%112,%113,%114,%115,%116,%117,%118,%119,%120,%121,%122,%123,%124,%125,%126,%127}"
#define R128(d, e) R8(d, 0), R8(d, 8), R8(d, 16), R8(d, 24), R8(d, 32), R8(d, 40), R8(d, 48), R8(d, 56), \
                   R8(e, 0), R8(e, 8), R8(e, 16), R8(e, 24), R8(e, 32), R8(e, 40), R8(e, 48), R8(e, 56)
__device__ __forceinline__ void mma256_ss(float (&d)[64], float (&e)[64], uint64_t da, uint64_t db, int sc) {
  asm volatile("{\n.reg .pred p;\nsetp.ne.b32 p, %130, 0;\n"
               "wgmma.mma_async.sync.aligned.m64n256k16.f32.bf16.bf16 " D128 ", %128, %129, p, 1, 1, 0, 1;\n}"
               : R128(d, e) : "l"(da), "l"(db), "r"(sc));
}
__device__ __forceinline__ void mma256_rs(float (&d)[64], float (&e)[64], uint32_t a0, uint32_t a1, uint32_t a2, uint32_t a3, uint64_t db) {
  asm volatile("{\n.reg .pred p;\nsetp.ne.b32 p, 1, 0;\n"
               "wgmma.mma_async.sync.aligned.m64n256k16.f32.bf16.bf16 " D128 ", {%128,%129,%130,%131}, %132, p, 1, 1, 1;\n}"
               : R128(d, e) : "r"(a0), "r"(a1), "r"(a2), "r"(a3), "l"(db));
}
template <int N> __device__ __forceinline__ void keep(float (&a)[N]) {
#pragma unroll
  for (int i = 0; i < N; i++) asm volatile("" : "+f"(a[i])::"memory");
}
template <int N> __device__ __forceinline__ void keep(uint32_t (&a)[N]) {
#pragma unroll
  for (int i = 0; i < N; i++) asm volatile("" : "+r"(a[i])::"memory");
}

#define PROF(cond, idx) do {} while (0)

constexpr float SCL2 = 1.4426950408889634f * 0.08838834764831845f;

__device__ __forceinline__ void pack_p(const float (&s)[64], uint32_t (&p)[32]) {
#pragma unroll
  for (int i = 0; i < 32; i++) p[i] = pack_bf(s[2 * i], s[2 * i + 1]);
}

__device__ __forceinline__ void issue_qk(float (&s)[64], uint32_t q0, uint32_t q1, uint32_t kslot) {
  const uint64_t db = make_desc(kslot, 16, 1024), da0 = make_desc(q0, 16, 1024), da1 = make_desc(q1, 16, 1024);
#pragma unroll
  for (int kk = 0; kk < 8; kk++) mma_ss<0>(s, (kk < 4 ? da0 : da1) + (kk & 3) * 2, db + (kk >> 2) * 1024 + (kk & 3) * 2, kk != 0);
}
__device__ __forceinline__ void issue_pv(float (&o)[64], uint32_t (&p)[32], uint32_t vslot, int acc) {
  uint64_t db = make_desc(vslot, 16384, 1024);
#pragma unroll
  for (int kk = 0; kk < 8; kk++)
    mma_rs<1>(o, p[4 * kk], p[4 * kk + 1], p[4 * kk + 2], p[4 * kk + 3], db + kk * 128, kk == 0 ? acc : 1);
}

template <int H>
__device__ __forceinline__ void store_chunk(const float (&a)[64], uint32_t addr) {
#pragma unroll
  for (int i = 8 * H; i < 8 * H + 8; i += 2)
    stmatrix4(addr ^ ((i & 7) << 4), pack_bf(a[4 * i], a[4 * i + 1]), pack_bf(a[4 * i + 2], a[4 * i + 3]),
              pack_bf(a[4 * i + 4], a[4 * i + 5]), pack_bf(a[4 * i + 6], a[4 * i + 7]));
}
template <int H>
__device__ __forceinline__ void store_chunk(const float (&a)[64], float i0, float i1, uint32_t addr) {
#pragma unroll
  for (int i = 8 * H; i < 8 * H + 8; i += 2)
    stmatrix4(addr ^ ((i & 7) << 4), pack_bf(a[4 * i] * i0, a[4 * i + 1] * i0), pack_bf(a[4 * i + 2] * i1, a[4 * i + 3] * i1),
              pack_bf(a[4 * i + 4] * i0, a[4 * i + 5] * i0), pack_bf(a[4 * i + 6] * i1, a[4 * i + 7] * i1));
}
__device__ __forceinline__ float inv_quad_sum(float l) {
  l += __shfl_xor_sync(0xffffffffu, l, 1);
  l += __shfl_xor_sync(0xffffffffu, l, 2);
  return __fdividef(1.f, l);
}

__device__ __forceinline__ void ln_scalars(float mean, float var, float& mb, float& sd) {
  mb = rbf(mean);
  sd = rbf(sqrtf(rbf(rbf(var) + 1e-5f)));
}

__global__ void __cluster_dims__(2, 1, 1) __launch_bounds__(384, 1) fused_kernel(const __grid_constant__ Maps maps, const Ptrs P) {
  extern __shared__ __align__(1024) uint8_t smem_raw[];
  const uint32_t base = smem_u32(smem_raw);
  const int tid = threadIdx.x, lane = tid & 31;
  const int warp = __shfl_sync(0xffffffffu, tid >> 5, 0);
  const int b = blockIdx.x;
  PROF(tid == 0, 0);

  if (b >= NMAIN) {
    float* sc = reinterpret_cast<float*>(smem_raw);
    float* red = sc + DM;
    for (int k = tid; k < DM; k += 384) sc[k] = rbf(silu_f(__bfloat162float(P.c[k])));
    __syncthreads();
    if (tid < 256) {
      const int col = 2048 + (b - NMAIN) * 1024 + (tid & 127) * 8, r0 = (tid >> 7) * 512;
      float acc[8];
#pragma unroll
      for (int e = 0; e < 8; e++) acc[e] = 0.f;
      for (int r = r0; r < r0 + 512; r += 32) {
        uint4 w[32];
#pragma unroll
        for (int u = 0; u < 32; u++) w[u] = ldg_nc4(P.w_mod + (size_t)(r + u) * NMOD + col);
#pragma unroll
        for (int u = 0; u < 32; u++) {
          float s = sc[r + u];
          acc[0] += s * bf_lo(w[u].x); acc[1] += s * bf_hi(w[u].x); acc[2] += s * bf_lo(w[u].y); acc[3] += s * bf_hi(w[u].y);
          acc[4] += s * bf_lo(w[u].z); acc[5] += s * bf_hi(w[u].z); acc[6] += s * bf_lo(w[u].w); acc[7] += s * bf_hi(w[u].w);
        }
      }
      if (tid >= 128) {
#pragma unroll
        for (int e = 0; e < 8; e++) red[(tid & 127) * 8 + e] = acc[e];
      }
      const uint32_t tag = ld_relaxed(&g_epoch) % 3 + 1;
      bar_sync(1, 256);
      if (tid < 128) {
        uint32_t o[8];
#pragma unroll
        for (int e = 0; e < 8; e++) o[e] = __float_as_uint(rbf(acc[e] + red[tid * 8 + e])) | tag;
        st_relaxed4(g_mod + col, o[0], o[1], o[2], o[3]);
        st_relaxed4(g_mod + col + 4, o[4], o[5], o[6], o[7]);
      }
    }
    PROF(tid == 0, 1);
    return;
  }

  const int rank = b & 1;
  const int rb = ((b >> 4) << 1) | rank, cj = (b >> 1) & 7;
  const uint32_t bfull = base + OFF_BAR, bempty = bfull + NSLOT * 8;
  const uint32_t gfull = bempty + NSLOT * 8, gempty = gfull + 32;
  const uint32_t bar_ofull = gempty + 32;
  const uint32_t bar_ofree = bar_ofull + 16;
  const uint32_t bar_par = bar_ofree + 32;
  const uint32_t bar_mod = bar_par + 8;
  const uint32_t bar_pread = bar_mod + 8;
  const uint32_t bar_xres = bar_pread + 8;
  const uint32_t bar_w1 = bar_xres + 8;
  const uint32_t bar_w2 = bar_w1 + 8;
  const uint32_t bar_last = bar_w2 + 8;
  const uint32_t bar_ring = bar_last + 16;
  const uint32_t bar_box = bar_ring + 8;
  const uint32_t bar_go = bar_box + 96;
  const uint32_t bar_go2 = bar_go + 16;
  const uint32_t bar_cnt = bar_go + 24;
  const uint32_t xfull = bar_go + 32, xempty = xfull + 32;
  const uint32_t bar_hw = xempty + 32, bar_hx = bar_hw + 8;
  const uint32_t bar_hpub = bar_hx + 16;
  const uint32_t bar_ring0 = bar_hpub + 8;
  const uint32_t bar_rst = bar_go + 8;
  const uint32_t stage = base + OFF_STAGE, par = base + OFF_PAR;

  if (tid == 256) {
    for (int s = 0; s < NSLOT; s++) { mbar_init(bfull + s * 8, 1); mbar_init(bempty + s * 8, 16); }
    for (int s = 0; s < 4; s++) { mbar_init(gfull + s * 8, 1); mbar_init(gempty + s * 8, 16); mbar_init(xfull + s * 8, 1); mbar_init(xempty + s * 8, 8); mbar_init(bar_ofree + s * 8, 1); }
    mbar_init(bar_ofull, 128); mbar_init(bar_ofull + 8, 128);
    mbar_init(bar_par, 64); mbar_init(bar_mod, 256); mbar_init(bar_pread, 8); mbar_init(bar_xres, 1);
    mbar_init(bar_w1, 1); mbar_init(bar_w2, 1); mbar_init(bar_last, 1); mbar_init(bar_last + 8, 1); mbar_init(bar_ring, 8); mbar_init(bar_go, 1); mbar_init(bar_go2, 1); mbar_init(bar_cnt, 1); mbar_init(bar_rst, 64); mbar_init(bar_hpub, 8); mbar_init(bar_ring0, 8);
    for (int s = 0; s < 12; s++) mbar_init(bar_box + s * 8, 1);
    asm volatile("fence.mbarrier_init.release.cluster;" ::: "memory");
    prefetch_map(&maps.x); prefetch_map(&maps.wq); prefetch_map(&maps.k); prefetch_map(&maps.v);
  }
  if (tid == 288) {
    mbar_init(bar_hw, 1); mbar_init(bar_hx, 1); mbar_init(bar_hx + 8, 1);
    asm volatile("fence.mbarrier_init.release.cluster;" ::: "memory");
    mbar_expect_tx(bar_hw, 32768);
    mbar_expect_tx(bar_hx, 16384);
    mbar_expect_tx(bar_hx + 8, 16384);
    const __nv_bfloat16* xs = P.x + (size_t)(rb * 128 + cj * 16) * DM;
    bulk_load(base + 2 * GST_BYTES, xs, 16384, bar_hx);
    tma2d(stage, &maps.wm, (b >> 1) * 32, rank * 512, bar_hw);
    tma2d(stage + 16384, &maps.wm, (b >> 1) * 32, rank * 512 + 256, bar_hw);
    bulk_load(base + 3 * GST_BYTES, xs + 8 * DM, 16384, bar_hx + 8);
  }
  cluster_arrive();

  if (warp >= 8) {
    asm volatile("setmaxnreg.dec.sync.aligned.u32 40;");
    if (warp < 10) bar_arrive(1, 320);
    cluster_wait();
    if (warp == 8) {
      if (lane == 0) {
        uint32_t gph = 1;
        const int kvrow = (cj >> 1) * SK + (SK - WIN);
        int wch = cj * 8 + rank * 2;
#pragma unroll 1
        for (int ps = 0; ps < 3; ps++) {
          const CUtensorMap* mw = ps == 2 ? &maps.wo : &maps.wq;
                    const uint32_t xt = ps == 1 ? XT1 : XT2, wt = ps == 0 ? WT0 : (ps == 1 ? WT1 : WT2);
          const int nst = ps == 2 ? 32 : 16;
          if (ps) {
            const uint32_t epoch = ld_relaxed(&g_epoch);
            wait_counter(ps == 1 ? &g_cnt_h[rb * 32] : &g_cnt_o[(rb * 8 + (cj & 1)) * 32], 8 * (epoch + 1));
            if (ps == 2) wait_counter(&g_cnt_o[(rb * 8 + 2 + (cj & 1)) * 32], 8 * (epoch + 1));
            fence_async();
            mbar_wait(bar_ofree + (ps - 1) * 16, 0);
          }
#pragma unroll 1
          for (int i = 0; i < nst; i++) {
            if (i == GOST) mbar_arrive(bar_go);
            if (ps == 0 && i == HD) mbar_wait(bar_mod, 0);
            if (ps && i && i < 4) mbar_wait(bempty + (i == 3 ? 3 : i - 1) * 8, 1);
            const uint32_t bf = i < 30 ? gfull + (i & 3) * 8 : bar_last + (i & 1) * 8;
            mbar_wait(gempty + (i & 3) * 8, gph);
            mbar_expect_tx(bf, ps ? GST_BYTES : 2 * UNIT);
            const int kt = ps == 2 ? (((cj & 1) * 4 + ((i >> 1) & 3)) * 4 + (i >> 3)) * 2 + (i & 1) : (i + (ps ? 0 : b & 14)) & 15;
            tma3d_mc<true>(base + unit_of(wt, i & 3) + rank * UNIT, mw, 0, kt * 64, wch, bf);
            if (i == 16) mbar_wait(bar_cnt, 0);
            if (ps && i == 2) mbar_wait(bempty + 16, 1);
            if (ps) bulk_load_stream(base + unit_of(xt, i & 3), g_act + (uint32_t)(rb * 80 + (ps - 1) * 16 + kt) * UNIT, UNIT, bf);
            if ((i & 3) == 3) gph ^= 1;
          }
          if (ps == 2) break;
          if (ps == 1) mbar_arrive(bar_go2);
          wch = ps ? ((wch >> 3) ^ rank) * 2 : wch + 4;
#pragma unroll 1
          for (int u = 0; u < 16; u++) {
            const bool isk = (u == 0) || ((u & 1) && u < 15);
            const int blk = (isk ? (u + 1) >> 1 : (u == 15 ? 7 : (u >> 1) - 1)) & 3;
            const uint32_t sl = base + unit_of(ps ? AT1 : AT0, u & 3), bf = bfull + (u & 3) * 8;
            if (u < 4) mbar_wait(gempty + ((u + 1) >> 1) * 8, gph);
            mbar_wait(bempty + (u & 3) * 8, ((u >> 2) & 1) ^ 1);
            mbar_expect_tx(bf, SLOT_BYTES);
            tma3d_mc<false>(sl + rank * 16384, isk ? &maps.k : &maps.v, 0, kvrow + blk * 128, rank, bf);
          }
        }
        if (b < NFFN) {
          mbar_wait(bar_ring0, 0);
#pragma unroll 1
          for (int u = 0; u < 12 + FPACE; u++) {
            if (u == E0) mbar_wait(bar_ring, 0);
            if (u >= FPACE) {
              mbar_wait(bar_box + (u - FPACE) * 8, 0);
              if (u - FPACE == 7) { mbar_arrive(bar_w1); PROF(true, 59); }
              if (u - FPACE == 11) { mbar_arrive(bar_w2); PROF(true, 60); }
            }
            if (u < 12) {
              mbar_expect_tx(bar_box + u * 8, UNIT);
              if (u < 8) tma2d(base + OFF_GATE + u * UNIT, u < 4 ? &maps.wg : &maps.wu, b * 32, (u & 3) * 256, bar_box + u * 8);
              else tma3d(base + (u - 8) * UNIT, &maps.wd, 0, b * 32, (u - 8) * 4, bar_box + u * 8);
            }
          }
        }
      }
    } else if (warp == 9) {
      if (lane == 0) {
        const uint32_t epoch = ld_relaxed(&g_epoch);
#pragma unroll 1
        for (int i = 0; i < 16; i++) {
          if (i == HDX) mbar_wait(bar_mod, 0);
          if (i == NRS) {
            wait_counter(&g_cnt_h[rb * 32], 8 * (epoch + 1));
            PROF(true, 26);
            fence_async();
            PROF(true, 15);
          }
          mbar_wait(xempty + (i & 3) * 8, ((i >> 2) & 1) ^ 1);
          mbar_expect_tx(xfull + (i & 3) * 8, UNIT);
          if (i < NRS) tma2d(base + (i & 3) * GST_BYTES, &maps.x, ((2 * cj + i) & 15) * 64, rb * 128, xfull + (i & 3) * 8);
          else bulk_load_stream(base + (i & 3) * GST_BYTES, g_act + (uint32_t)(rb * 80 + ((2 * cj + i) & 15)) * UNIT, UNIT, xfull + (i & 3) * 8);
        }
        prefetch_map(&maps.wo);
#pragma unroll 1
        for (int t = 0; t < 4; t++) {
#pragma unroll 1
          for (int w = 0; w < 2; w++) {
            mbar_wait(bar_ofull + w * 8, t & 1);
            uint8_t* dst = g_act + (uint32_t)(rb * 80 + 16 + (cj * 4 + t) * 2) * UNIT + w * 8192;
            bulk_store(dst, base + unit_of(QT, 2 * t) + w * 8192, 8192);
            bulk_store(dst + UNIT, base + unit_of(QT, 2 * t + 1) + w * 8192, 8192);
            asm volatile("cp.async.bulk.commit_group;" ::: "memory");
          }
          asm volatile("cp.async.bulk.wait_group.read 0;" ::: "memory");
          mbar_arrive(bar_ofree + t * 8);
          if (t == 3) {
            mbar_expect_tx(bar_xres, 32768);
            tma2d(base + OFF_RES, &maps.x, cj * 128, rb * 128, bar_xres);
            tma2d(base + OFF_RES + UNIT, &maps.x, cj * 128 + 64, rb * 128, bar_xres);
          }
          asm volatile("cp.async.bulk.wait_group 0;" ::: "memory");
          fence_async();
          red_release(&g_cnt_o[((rb * 4 + t) * 2 + (cj >> 2)) * 32], 2);
          if (t == PF2T) for (int u = 0; u < PF2; u++)
            tma3d_prefetch(&maps.wo, 0, ((((cj & 1) * 4 + (b >> 5)) * 4 + u) * 2 + ((b >> 4) & 1)) * 64, (cj ^ rank) * 2);
        }
        wait_counter(&g_cnt_o[(rb * 8 + 4 + (cj & 1)) * 32], 8 * (epoch + 1));
        wait_counter(&g_cnt_o[(rb * 8 + 6 + (cj & 1)) * 32], 8 * (epoch + 1));
        fence_async();
        mbar_arrive(bar_cnt);
        PROF(true, 27);
      }
      __syncwarp();
      mbar_wait(bar_last, 0);
      bar_arrive(8, 160); bar_arrive(9, 160);
      mbar_wait(bar_last + 8, 0);
      bar_arrive(10, 160); bar_arrive(11, 160);
    } else {
      const int t2 = tid - 320;
      if (t2 == 0) {
        mbar_wait(bar_hpub, 0);
        PROF(true, 24);
        red_release(&g_cnt_h[rb * 32], 1);
        PROF(true, 25);
        prefetch_map(&maps.wg); prefetch_map(&maps.wu); prefetch_map(&maps.wd);
      }
      __syncwarp();
      if (b < NFFN) {
        mbar_wait(bar_go2, 0);
        const __nv_bfloat16* pg = ((b & 1) ? P.w_up : P.w_gate) + (b >> 1) * 64 + (size_t)t2 * FF;
        const __nv_bfloat16* pd = P.w_down + (size_t)b * 32768 + t2 * 64;
        PROF(t2 == 0, 13);
#pragma unroll 1
        for (int i = 0; i < WN; i += WB) {
          uint32_t v[WB];
#pragma unroll
          for (int u = 0; u < WB; u++)
            asm volatile("ld.global.cg.L2::128B.u32 %0, [%1];" : "=r"(v[u]) : "l"(i < 16 ? pg + (size_t)(i + u) * 64 * FF : pd + (i + u - 16) * 4096));
#pragma unroll
          for (int u = 1; u < WB; u++) v[0] ^= v[u];
          sts1(par + PAR_SINK + t2 * 4, v[0]);
        }
        PROF(t2 == 0, 14);
      }
      const uint32_t epoch = ld_relaxed(&g_epoch), tag = epoch % 3 + 1;
      mbar_wait(bar_xres, 0);
      float s1 = 0.f, s2 = 0.f;
#pragma unroll 1
      for (int q = 0; q < 4; q++) {
        const int col = q * 256 + t2 * 4;
        uint4 vsb = poll4(g_mod + 3 * DM + col, tag), vcb = poll4(g_mod + 4 * DM + col, tag);
        uint2 wr = *reinterpret_cast<const uint2*>(P.w_r + col);
        float c0 = rbf(1.f + bf_hi(vcb.x)), c1 = rbf(1.f + bf_hi(vcb.y)), c2 = rbf(1.f + bf_hi(vcb.z)), c3 = rbf(1.f + bf_hi(vcb.w));
        float a0 = c0 * bf_lo(wr.x), a1 = c1 * bf_hi(wr.x), a2 = c2 * bf_lo(wr.y), a3 = c3 * bf_hi(wr.y);
        s1 += (a0 + a1) + (a2 + a3);
        s2 += bf_hi(vsb.x) * bf_lo(wr.x) + bf_hi(vsb.y) * bf_hi(wr.x) + bf_hi(vsb.z) * bf_lo(wr.y) + bf_hi(vsb.w) * bf_hi(wr.y);
        if ((col >> 7) == cj) {
          const int lc = col & 127;
          uint4 vga = poll4(g_mod + 2 * DM + col, tag), vgb = poll4(g_mod + 5 * DM + col, tag);
          sts2(par + PAR_GA + lc * 2, __byte_perm(vga.x, vga.y, 0x7632), __byte_perm(vga.z, vga.w, 0x7632));
          sts2(par + PAR_GB + lc * 2, __byte_perm(vgb.x, vgb.y, 0x7632), __byte_perm(vgb.z, vgb.w, 0x7632));
          sts2(par + PAR_SB + lc * 2, __byte_perm(vsb.x, vsb.y, 0x7632), __byte_perm(vsb.z, vsb.w, 0x7632));
          sts2(par + PAR_CB1 + lc * 2, pack_bf(c0, c1), pack_bf(c2, c3));
          sts4(par + PAR_A + lc * 4, make_uint4(__float_as_uint(a0), __float_as_uint(a1), __float_as_uint(a2), __float_as_uint(a3)));
        }
      }
#pragma unroll
      for (int o = 16; o > 0; o >>= 1) { s1 += __shfl_xor_sync(0xffffffffu, s1, o); s2 += __shfl_xor_sync(0xffffffffu, s2, o); }
      if (lane == 0) { sts2(par + PAR_CONST + (warp - 10) * 8, __float_as_uint(s1), __float_as_uint(s2)); sts1(par + PAR_CONST + 48, epoch); }
      if (t2 < 2) {
        uint4 g = poll4(g_mod + 5 * DM + b * 8 + t2 * 4, tag);
        sts4(par + PAR_CONST + 16 + t2 * 16, g);
      }
      mbar_wait(bar_go, 0);
      for (int q = XR; q < XE; q++) st_b128(g_xch + ((size_t)b * 8 * 256 + q * 64 + t2) * 4, (epoch & 1) << 16, 0, 0, 0);
      for (int q = 0; q < 2; q++) st_relaxed4(g_stats + ((size_t)cj * SEQ + rb * 128 + q * 64 + t2) * 4, 0, 0, 0, 0);
      __threadfence();
      mbar_arrive(bar_par);
      mbar_wait(bar_ring, 0);
      if (b < NFFN)
        for (int q = 0; q < 4; q++) st_relaxed4(g_ypart + ((size_t)(q * 32 + (t2 >> 1)) * NFFN + b) * 8 + (t2 & 1) * 4, 0, 0, 0, 0);
      st_relaxed4(g_row + rb * 2 * DM + (t2 >> 5) * DM + cj * 128 + (t2 & 31) * 4, 0, 0, 0, 0);
      if (cj == 0 && t2 < 2) st_relaxed4(g_cand + rb * 8 + t2 * 4, 0, 0, 0, 0);
      __threadfence();
      mbar_arrive(bar_rst);
    }
    __syncwarp();
    cluster_arrive();
    cluster_wait();
  } else {
    const int wg = warp >> 2;

    uint32_t tag;
    {
      uint32_t* const pmod = g_modp + rank * 2 * DM + (b >> 1) * 32 + lane;
      uint32_t* const pln = g_ln1 + (rb * 128 + cj * 16 + warp) * 4;
      const uint32_t cv = ldg_nc1(P.c + rank * 512 + tid * 2);
      const uint32_t epoch = ld_relaxed(&g_epoch);
      if (warp == 0) st_relaxed(pmod, 0);
      if (lane == 0) { st_relaxed2(pln, 0, 0); st_relaxed2(pln + 32, 0, 0); }
      asm volatile("setmaxnreg.inc.sync.aligned.u32 232;");
      sts1(par + tid * 4, pack_bf(silu_f(bf_lo(cv)), silu_f(bf_hi(cv))));
      bar_sync(1, 320);
      tag = epoch % 3 + 1;
#pragma unroll
      for (int part = 0; part < 3; part++) {
        if (part != 1) {
          const uint32_t xa = base + (2 + part / 2) * GST_BYTES + warp * 2048 + lane * 16;
          mbar_wait(bar_hx + part * 4, 0);
          float s0 = 0.f, s1 = 0.f, q0 = 0.f, q1 = 0.f;
#pragma unroll
          for (int q = 0; q < 4; q++) {
            const uint4 xv = lds4(xa + q * 512);
            const uint32_t u[4] = {xv.x, xv.y, xv.z, xv.w};
#pragma unroll
            for (int e = 0; e < 4; e++) { const float lo = bf_lo(u[e]), hi = bf_hi(u[e]); s0 += lo; s1 += hi; q0 += lo * lo; q1 += hi * hi; }
          }
          s0 += s1; q0 += q1;
#pragma unroll
          for (int o = 16; o > 0; o >>= 1) { s0 += __shfl_xor_sync(0xffffffffu, s0, o); q0 += __shfl_xor_sync(0xffffffffu, q0, o); }
          const float mean = s0 * (1.f / DM);
          float mb, sd;
          ln_scalars(mean, fmaxf(q0 * (1.f / DM) - mean * mean, 0.f), mb, sd);
          if (lane == 0) st_relaxed2(pln + part * 16, __float_as_uint(mb) | tag, __float_as_uint(sd) | tag);
          PROF(tid == 0 && part == 2, 4);
        } else {
          float acc[8];
#pragma unroll
          for (int e = 0; e < 8; e++) acc[e] = 0.f;
          const uint32_t wa = stage + (tid >> 2) * 64 + (((tid ^ (tid >> 3)) & 3) << 4), sa = par + (tid >> 3) * 4, sh = (tid & 4) ? 0x3244 : 0x1044;
          mbar_wait(bar_hw, 0);
#pragma unroll
          for (int p = 0; p < 8; p++) {
            const uint4 w = lds4(wa + p * 4096);
            const float s = __uint_as_float(__byte_perm(lds1(sa + p * 128), 0, sh));
            acc[0] += s * bf_lo(w.x); acc[1] += s * bf_hi(w.x); acc[2] += s * bf_lo(w.y); acc[3] += s * bf_hi(w.y);
            acc[4] += s * bf_lo(w.z); acc[5] += s * bf_hi(w.z); acc[6] += s * bf_lo(w.w); acc[7] += s * bf_hi(w.w);
          }
#pragma unroll
          for (int e = 0; e < 4; e++) {
            const bool up = lane & 16;
            acc[e] = (up ? acc[e + 4] : acc[e]) + __shfl_xor_sync(0xffffffffu, up ? acc[e] : acc[e + 4], 16);
          }
#pragma unroll
          for (int e = 0; e < 2; e++) {
            const bool up = lane & 8;
            acc[e] = (up ? acc[e + 2] : acc[e]) + __shfl_xor_sync(0xffffffffu, up ? acc[e] : acc[e + 2], 8);
          }
          {
            const bool up = lane & 4;
            acc[0] = (up ? acc[1] : acc[0]) + __shfl_xor_sync(0xffffffffu, up ? acc[0] : acc[1], 4);
          }
          sts1(par + 1024 + warp * 128 + ((lane & 3) * 8 + (lane >> 2)) * 4, __float_as_uint(acc[0]));
          bar_sync(1, 256);
          if (warp == 0) {
            float s = 0.f;
#pragma unroll
            for (int w8 = 0; w8 < 8; w8++) s += __uint_as_float(lds1(par + 1024 + w8 * 128 + lane * 4));
            st_relaxed(pmod, (__float_as_uint(s) & ~3u) | tag);
          }
          PROF(tid == 0, 3);
        }
      }
      {
        uint2 s0 = ld_relaxed2(g_ln1 + (rb * 128 + (tid & 127)) * 4);
        uint4 v[4];
#pragma unroll
        for (int q = 0; q < 4; q++) v[q] = ld_relaxed4(g_modp + q * DM + tid * 4);
        {
          uint32_t n = 0;
          while (!(tag_ok(v[0], tag) && tag_ok(v[1], tag) && tag_ok(v[2], tag) && tag_ok(v[3], tag))) {
#pragma unroll
            for (int q = 0; q < 4; q++)
              if (!tag_ok(v[q], tag)) v[q] = ld_relaxed4(g_modp + q * DM + tid * 4);
            if (((s0.x ^ tag) | (s0.y ^ tag)) & 3u) s0 = ld_relaxed2(g_ln1 + (rb * 128 + (tid & 127)) * 4);
            watchdog(n);
          }
        }
        const uint32_t d = stage + (tid >> 2) * 64 + (tid & 1) * 32 + (tid & 2) * 2;
        sts1(d, pack_bf(1.f + rbf(untag_sum(v[1].x, v[3].x)), 1.f + rbf(untag_sum(v[1].y, v[3].y))));
        sts1(d + 16, pack_bf(1.f + rbf(untag_sum(v[1].z, v[3].z)), 1.f + rbf(untag_sum(v[1].w, v[3].w))));
        sts1(d + 8, pack_bf(untag_sum(v[0].x, v[2].x), untag_sum(v[0].y, v[2].y)));
        sts1(d + 24, pack_bf(untag_sum(v[0].z, v[2].z), untag_sum(v[0].w, v[2].w)));
        if (wg == 0) {
          uint32_t n = 0;
          while (((s0.x ^ tag) | (s0.y ^ tag)) & 3u) { s0 = ld_relaxed2(g_ln1 + (rb * 128 + tid) * 4); watchdog(n); }
          uint32_t ih, il;
          split_inv(bf_hi(s0.y), ih, il);
          sts4(stage + 4096 + tid * 16, make_uint4(__byte_perm(s0.x, 0, 0x3232), ih, il, 0));
        }
        mbar_arrive(bar_mod);
      }
      cluster_wait();
      if (wg == 1) bar_arrive(2, 256);
      mbar_wait(bar_mod, 0);
      PROF(tid == 0, 2);
    }

    float f0 = 0.f, f1 = 0.f;
    const uint32_t rempty = lane < 2 ? mapa(bempty, lane & 1) : 0;
    constexpr uint32_t GE = NSLOT * 8 + 32;
    float o[64], s[64];
#pragma unroll 1
    for (int ps = 0; ps < 3; ps++) {
      {
        const uint32_t xt = ps == 1 ? XT1 : XT2, wt = ps == 1 ? WT1 : WT2;
        const int nst = ps == 2 ? 28 : 14;
        if (ps == 0) {
          float ga[64], gb[64];
#pragma unroll
          for (int i = 0; i < 64; i++) { ga[i] = 0.f; gb[i] = 0.f; }
          uint32_t a[2][16];
          const uint32_t l = fresh_lane();
          const uint4 r0 = lds4(stage + 4096 + (warp * 16 + (l >> 2)) * 16), r1 = lds4(stage + 4096 + 128 + (warp * 16 + (l >> 2)) * 16);
          auto transform = [&](int i, uint32_t (&f)[16], uint32_t z) {
            const uint32_t ad = base + (i & 3) * GST_BYTES + wg * 8192 + frag_offset(warp) + z;
            mbar_wait(xfull + (i & 3) * 8, i >> 2);
#pragma unroll
            for (int kk = 0; kk < 4; kk++) ldmatrix4(ad ^ (kk * 32), f[4 * kk], f[4 * kk + 1], f[4 * kk + 2], f[4 * kk + 3]);
#pragma unroll
            for (int kk = 0; kk < 4; kk++) {
              const uint4 m = lds4(stage + (l & 3) * 16 + ((2 * cj + i) & 15) * 256 + kk * 64);
              f[4 * kk] = ln_mod(f[4 * kk], r0.x, r0.y, r0.z, m.x, m.z);
              f[4 * kk + 1] = ln_mod(f[4 * kk + 1], r1.x, r1.y, r1.z, m.x, m.z);
              f[4 * kk + 2] = ln_mod(f[4 * kk + 2], r0.x, r0.y, r0.z, m.y, m.w);
              f[4 * kk + 3] = ln_mod(f[4 * kk + 3], r1.x, r1.y, r1.z, m.y, m.w);
            }
            keep(f);
            mbar_arrive_pred(xempty + (i & 3) * 8, l == 0);
          };
          auto publish = [&](int u, uint32_t (&f)[16]) {
            const uint32_t sc = stage + 8192 + wg * 8192;
#pragma unroll
            for (int kk = 0; kk < 4; kk++) stmatrix4((sc + frag_offset(warp)) ^ (kk * 32), f[4 * kk], f[4 * kk + 1], f[4 * kk + 2], f[4 * kk + 3]);
            __syncwarp();
            const uint32_t src = sc + (warp & 3) * 2048 + l * 16;
            uint8_t* dst = g_act + (uint32_t)(rb * 80 + cj * 2 + u) * UNIT + warp * 2048 + l * 16;
#pragma unroll
            for (int p4 = 0; p4 < 4; p4++) stg4(dst + p4 * 512, lds4(src + p4 * 512));
            __syncwarp();
            if (u == 1) mbar_arrive_pred(bar_hpub, l == 0);
          };
          auto multiply = [&](int i, uint32_t (&f)[16]) {
            mbar_wait(gfull + (i & 3) * 8, i >> 2);
            const uint64_t db = make_desc(base + (i & 3) * GST_BYTES + UNIT, 8192, 1024);
            wg_fence();
#pragma unroll
            for (int kk = 0; kk < 4; kk++) mma256_rs(ga, gb, f[4 * kk], f[4 * kk + 1], f[4 * kk + 2], f[4 * kk + 3], db + kk * 128);
            wg_commit();
          };
          transform(0, a[0], 0); publish(0, a[0]); transform(1, a[1], 0); multiply(0, a[0]); publish(1, a[1]);
#pragma unroll
          for (int i = 1; i < NRS; i++) {
            if (i >= 2) {
              uint32_t z = r0.w;
#pragma unroll
              for (int k = 0; k < 16; k += 2) asm volatile("lop3.b32 %0, %1, %2, %0, 0xA8;" : "+r"(z) : "r"(a[i & 1][k]), "r"(a[i & 1][k + 1]));
              transform(i, a[i & 1], z);
            }
            multiply(i, a[i & 1]);
            wg_wait<1>();
            mbar_arrive_cl(rempty, GE + ((i + 3) & 3) * 8);
          }
          mbar_arrive_pred(bar_pread, l == 0);
#pragma unroll 1
          for (int i = NRS; i < 14; i++) {
            mbar_wait(xfull + (i & 3) * 8, (i >> 2) & 1);
            mbar_wait(gfull + (i & 3) * 8, (i >> 2) & 1);
            const uint32_t xa = base + (i & 3) * GST_BYTES;
            const uint64_t da = make_desc(xa + wg * 8192, 16, 1024), db = make_desc(xa + UNIT, 8192, 1024);
            if (i == 13) bar_sync(2 + wg, 256);
            wg_fence();
#pragma unroll
            for (int kk = 0; kk < 4; kk++) mma256_ss(ga, gb, da + kk * 2, db + kk * 128, 1);
            wg_commit();
            if (i == 13) bar_arrive(3 - wg, 256);
            wg_wait<1>();
            uint32_t z = r0.w;
#pragma unroll
            for (int k = 0; k < 16; k += 2) asm volatile("lop3.b32 %0, %1, %2, %0, 0xA8;" : "+r"(z) : "r"(a[1][k]), "r"(a[1][k + 1]));
            mbar_arrive_cl(rempty, GE + ((i + 3) & 3) * 8 + z);
            mbar_arrive_pred(xempty + ((i + 3) & 3) * 8, l == 0 && i != NRS);
          }
          mbar_wait(xfull + 16, 1);
          mbar_wait(xfull + 24, 1);
          wg_wait<0>();
          keep(ga); keep(gb);
#pragma unroll
          for (int i = 0; i < 64; i++) {
            asm volatile("mov.b32 %0, %1;" : "=f"(s[i]) : "f"(ga[i]));
            asm volatile("mov.b32 %0, %1;" : "=f"(o[i]) : "f"(gb[i]));
          }
        } else {
          float ga[64], gb[64];
#pragma unroll
          for (int i = 0; i < 64; i++) {
            asm volatile("mov.b32 %0, %1;" : "=f"(ga[i]) : "f"(s[i]));
            asm volatile("mov.b32 %0, %1;" : "=f"(gb[i]) : "f"(o[i]));
          }
#pragma unroll 1
          for (int i = 0; i < nst; i++) {
            mbar_wait(gfull + (i & 3) * 8, (i >> 2) & 1);
            const uint64_t da = make_desc(base + unit_of(xt, i & 3) + wg * 8192, 16, 1024), db = make_desc(base + unit_of(wt, i & 3), 8192, 1024);
            if (i == nst - 1) bar_sync(2 + wg, 256);
            wg_fence();
#pragma unroll
            for (int kk = 0; kk < 4; kk++) mma256_ss(ga, gb, da + kk * 2, db + kk * 128, kk ? 1 : i);
            wg_commit();
            if (i == nst - 1) bar_arrive(3 - wg, 256);
            wg_wait<1>();
            mbar_arrive_cl(rempty, GE + ((i + 3) & 3) * 8, i != 0);
            PROF(tid == 0 && (i & 3) == 0, 40 + (ps - 1) * 4 + i / 4);
          }
          wg_wait<0>();
          keep(ga); keep(gb);
#pragma unroll
          for (int i = 0; i < 64; i++) {
            asm volatile("mov.b32 %0, %1;" : "=f"(s[i]) : "f"(ga[i]));
            asm volatile("mov.b32 %0, %1;" : "=f"(o[i]) : "f"(gb[i]));
          }
        }
        mbar_arrive_cl(rempty, GE + (ps == 2 ? 24 : 8));
        if (ps == 2) break;
      }
      const uint32_t qw = base + wg * 8192, qt = QT >> (16 * ps), at = ps ? AT1 : AT0;
      {
        const uint32_t wt = ps ? WT1 : WT0;
        const uint64_t da0 = make_desc(qw + unit_of(qt, 2), 16, 1024), da1 = make_desc(qw + unit_of(qt, 3), 16, 1024);
        const uint64_t db0 = make_desc(base + unit_of(wt, 2), 8192, 1024), db1 = make_desc(base + unit_of(wt, 3), 8192, 1024);
        mbar_wait(gfull + 16, 1);
        mbar_wait(gfull + 24, 1);
        bar_sync(2 + wg, 256);
        wg_fence();
#pragma unroll
        for (int kk = 0; kk < 8; kk++) mma_ss<1>(s, (kk < 4 ? da0 : da1) + (kk & 3) * 2, (kk < 4 ? db0 : db1) + (kk & 3) * 128, 1);
        wg_commit();
        bar_arrive(3 - wg, 256);
        mbar_wait(ps == 0 ? bar_pread : bar_ofree + 8, 0);
        mbar_wait(bfull, 0);
        wg_wait<0>();
        keep(s);
        PROF(tid == 0, 8 + ps * 8);
        store_chunk<0>(s, qw + unit_of(qt, 0) + frag_offset(warp));
        store_chunk<1>(s, qw + unit_of(qt, 1) + frag_offset(warp));
        fence_async_smem();
        bar_sync(2 + wg, 256);
        wg_fence();
        issue_qk(s, qw + unit_of(qt, 0), qw + unit_of(qt, 1), base + unit_of(at, 0));
        wg_commit();
#pragma unroll
        for (int kk = 0; kk < 8; kk++) mma_ss<1>(o, (kk < 4 ? da0 : da1) + (kk & 3) * 2, (kk < 4 ? db0 : db1) + UNIT / 16 + (kk & 3) * 128, 1);
        wg_commit();
        bar_arrive(3 - wg, 256);
        wg_wait<1>();
        keep(s);
        mbar_arrive_cl(rempty, 0);
      }
      PROF(tid == 0 && ps == 1, 61);
      float l0 = 0.25f, l1 = 0.25f;
      auto step = [&](auto odd_c, const int j, uint32_t (&pw)[32], uint32_t (&pr)[32]) {
        constexpr bool ODD = decltype(odd_c)::value;
        const bool first = !ODD && (j & 2) == 0, last = ODD && j == 7;
        const uint32_t ph = (j >> 1) & 1;
        float i0, i1, a0, a1;
        if (first) { i0 = inv_quad_sum(l0); i1 = inv_quad_sum(l1); l0 = 0.f; l1 = 0.f; }
        bool redo = !ODD && (j | ps) == 0, again = false;
        while (true) {
          if (redo) {
            float m0 = fmaxf(s[0], s[1]), m1 = fmaxf(s[2], s[3]);
#pragma unroll
            for (int i = 1; i < 16; i++) { m0 = fmaxf(m0, fmaxf(s[4 * i], s[4 * i + 1])); m1 = fmaxf(m1, fmaxf(s[4 * i + 2], s[4 * i + 3])); }
            m0 = fmaxf(m0, __shfl_xor_sync(0xffffffffu, m0, 1)); m1 = fmaxf(m1, __shfl_xor_sync(0xffffffffu, m1, 1));
            m0 = fmaxf(m0, __shfl_xor_sync(0xffffffffu, m0, 2)); m1 = fmaxf(m1, __shfl_xor_sync(0xffffffffu, m1, 2));
            m0 *= SCL2; m1 *= SCL2;
            if (!first) {
              m0 = fmaxf(m0, f0); m1 = fmaxf(m1, f1);
              const float c0 = ex2(f0 - m0), c1 = ex2(f1 - m1);
              l0 *= c0; l1 *= c1;
              wg_wait<0>();
              keep(o);
#pragma unroll
              for (int i = 0; i < 16; i++) { o[4 * i] *= c0; o[4 * i + 1] *= c0; o[4 * i + 2] *= c1; o[4 * i + 3] *= c1; }
            }
            f0 = m0; f1 = m1;
          }
          float b0 = 0.f, b1 = 0.f;
          a0 = 0.f; a1 = 0.f;
#pragma unroll
          for (int i = 0; i < 16; i++) {
            const float e0 = ex2(fmaf(s[4 * i], SCL2, -f0)), e1 = ex2(fmaf(s[4 * i + 1], SCL2, -f0));
            const float e2 = ex2(fmaf(s[4 * i + 2], SCL2, -f1)), e3 = ex2(fmaf(s[4 * i + 3], SCL2, -f1));
            a0 += e0; b0 += e1; a1 += e2; b1 += e3;
            pw[2 * i] = pack_bf(e0, e1); pw[2 * i + 1] = pack_bf(e2, e3);
            if (i == VREL) {
#pragma unroll
              for (int k = 0; k < 2 * VREL + 2; k++) asm volatile("" : "+r"(pw[k])::"memory");
              mbar_wait(bfull + (ODD ? 24 : 8), ph);
              wg_wait<0>();
              mbar_arrive_cl(rempty, ODD ? 16 : (j ? 0 : GE + 16), !again);
              if (!ODD) mbar_arrive_cl(rempty, GE + 24, !again && j == 0);
#pragma unroll
              for (int k = 4 * VREL + 4; k < 64; k++) asm volatile("" : "+f"(s[k])::"memory");
            }
          }
          a0 += b0; a1 += b1;
          if (redo) break;
          redo = __any_sync(0xffffffffu, !(a0 + a1 < 0x1p70f));
          if (first) {
            uint32_t m0 = __ballot_sync(0xffffffffu, a0 > 0x1p-50f), m1 = __ballot_sync(0xffffffffu, a1 > 0x1p-50f);
            m0 |= m0 >> 1; m1 |= m1 >> 1; m0 |= m0 >> 2; m1 |= m1 >> 2;
            redo = redo || (m0 & m1 & 0x11111111u) != 0x11111111u;
          }
          if (!redo) break;
          again = true;
        }
        l0 += a0; l1 += a1;
        keep(pw);
        keep(o);
        const uint32_t qo = qt >> (j ? 0 : 8);
        if (first) store_chunk<0>(o, i0, i1, qw + unit_of(qo, 0) + frag_offset(warp));
        keep(o);
        bar_sync(2 + wg, 256);
        if (!last) {
          const uint32_t qn = qt >> (j >= 3 ? 8 : 0);
          wg_fence();
          issue_qk(s, qw + unit_of(qn, 0), qw + unit_of(qn, 1), base + unit_of(at, ODD ? 3 : 1));
          wg_commit();
          mbar_wait(bfull + (ODD ? 0 : 16), ODD ? ph ^ 1 : ph);
        }
        if (first) { store_chunk<1>(o, i0, i1, qw + unit_of(qo, 1) + frag_offset(warp)); keep(o); }
        wg_fence();
        issue_pv(o, pw, base + unit_of(at, ODD ? (last ? 3 : 0) : 2), !first);
        wg_commit();
        bar_arrive(3 - wg, 256);
        if (first) { fence_async_smem(); mbar_arrive_pred(bar_ofull + wg * 8, j); PROF(tid == 0 && j, 9 + ps * 8); }
        wg_wait<1>();
        keep(s);
        mbar_arrive_cl(rempty, ODD ? 24 : 8, !last);
        PROF(tid == 0 && ps == 1, 51 + j);
      };
      uint32_t pa[32], pb[32];
#pragma unroll 1
      for (int j = 0; j < 8; j += 2) {
        step(std::false_type{}, j, pa, pb);
        step(std::true_type{}, j + 1, pb, pa);
      }
      {
        const float i0 = inv_quad_sum(l0), i1 = inv_quad_sum(l1);
        wg_wait<0>();
        keep(o);
        mbar_arrive_cl(rempty, 24);
        store_chunk<0>(o, i0, i1, qw + unit_of(qt, 2) + frag_offset(warp));
        store_chunk<1>(o, i0, i1, qw + unit_of(qt, 3) + frag_offset(warp));
        fence_async_smem();
        mbar_arrive(bar_ofull + wg * 8);
      }
      PROF(tid == 0, 10 + ps * 8);
    }

    const int ln = fresh_lane(), g = ln >> 2, tq = ln & 3, ct = warp * 32 + ln;
    const bool lane0 = ln == 0;
    const int lrow0 = warp * 16 + g;
    const int grow0 = rb * 128 + lrow0;
    const uint32_t res = base + OFF_RES, trow = res + wg * 8192 + frag_offset(warp);
    uint32_t xr[32];
    {
      const uint64_t da = make_desc(base + wg * 8192, 16, 1024), db = make_desc(base, 8192, 1024);
      constexpr int U = UNIT / 16;
      constexpr int XU[4] = {6, 9, 12, 13}, WU[4] = {7, 10, 0, 2};
#define HALF_STAGE(acc, st, hf) _Pragma("unroll") for (int kk = 0; kk < 4; kk++) mma_ss<1>(acc, da + XU[st] * U + kk * 2, db + (WU[st] + hf) * U + kk * 128, 1)
      PROF(ct == 0, 19);
      mbar_wait(gfull, 1);
      mbar_wait(gfull + 8, 1);
      wg_fence();
      HALF_STAGE(o, 0, 1);
      HALF_STAGE(o, 1, 1);
      bar_sync(8 + wg, 160);
      HALF_STAGE(o, 2, 1);
      HALF_STAGE(s, 0, 0);
      bar_sync(10 + wg, 160);
      HALF_STAGE(o, 3, 1);
      wg_commit();
      HALF_STAGE(s, 1, 0);
      HALF_STAGE(s, 2, 0);
      wg_commit();
      wg_wait<1>();
      keep(o);
      mbar_arrive_pred(bar_ring0, lane0);
      PROF(ct == 0, 20);
      mbar_wait(bar_par, 0);
      uint32_t* xo = g_xch + ((size_t)b * 8 * 256 + ct) * 4;
      const uint32_t par1 = (~lds1(par + PAR_CONST + 48) & 1) << 16;
      uint32_t w[32];
      pack_p(o, w);
#pragma unroll
      for (int i = 0; i < 8; i++) w[4 * i] = (w[4 * i] & ~0x10000u) | par1;
      keep(w);
#pragma unroll
      for (int i = 0; i < 8; i++) st_b128(xo + i * 1024, w[4 * i], w[4 * i + 1], w[4 * i + 2], w[4 * i + 3]);
      wg_fence();
      HALF_STAGE(s, 3, 0);
      wg_commit();
      PROF(ct == 0, 21);
      const uint32_t* xi = g_xch + ((size_t)(b ^ 2) * 8 * 256 + ct) * 4;
      uint4 v[8];
      v[XF] = ld_b128(xi + XF * 1024);
      wg_wait<0>();
      keep(s);
      cluster_arrive();
      PROF(ct == 0, 23);
      uint32_t n = 0;
      while ((v[XF].x & 0x10000u) != par1) { v[XF] = ld_b128(xi + XF * 1024); watchdog(n); }
      PROF(ct == 0, 22);
      mbar_arrive_pred(bar_ring, lane0);
#pragma unroll
      for (int i = 0; i < 8; i++) if (i != XF) v[i] = ld_b128(xi + i * 1024);
      bool ok;
      do {
        ok = true;
#pragma unroll
        for (int i = 0; i < 8; i++)
          if (i != XF && (v[i].x & 0x10000u) != par1) { v[i] = ld_b128(xi + i * 1024); ok = false; }
        watchdog(n);
      } while (!ok);
#pragma unroll
      for (int i = 0; i < 8; i++) {
        s[8 * i] += bf_lo(v[i].x); s[8 * i + 1] += __uint_as_float(v[i].x & 0xfffe0000u); s[8 * i + 2] += bf_lo(v[i].y); s[8 * i + 3] += bf_hi(v[i].y);
        s[8 * i + 4] += bf_lo(v[i].z); s[8 * i + 5] += bf_hi(v[i].z); s[8 * i + 6] += bf_lo(v[i].w); s[8 * i + 7] += bf_hi(v[i].w);
      }
    }
    PROF(ct == 0, 28);
    mbar_wait(bar_xres, 0);
    float su0 = 0.f, su1 = 0.f, sq0 = 0.f, sq1 = 0.f, dt0 = 0.f, dt1 = 0.f;
#pragma unroll
    for (int i = 0; i < 16; i++) {
      if (!(i & 1)) {
        ldmatrix4((trow ^ ((i & 7) << 4)) + (i >> 3) * 16384, xr[2 * i], xr[2 * i + 1], xr[2 * i + 2], xr[2 * i + 3]);
      }
      const uint32_t ga = lds1(par + PAR_GA + (8 * i + 2 * tq) * 2);
      const uint2 av = lds2(par + PAR_A + (8 * i + 2 * tq) * 4);
      const uint32_t u0 = hadd2(xr[2 * i], hmul2(ga, pack_bf(s[4 * i], s[4 * i + 1])));
      const uint32_t u1 = hadd2(xr[2 * i + 1], hmul2(ga, pack_bf(s[4 * i + 2], s[4 * i + 3])));
      xr[2 * i] = u0; xr[2 * i + 1] = u1;
      const float a = bf_lo(u0), c = bf_hi(u0), d = bf_lo(u1), e = bf_hi(u1);
      su0 += a + c; su1 += d + e;
      sq0 += a * a + c * c; sq1 += d * d + e * e;
      dt0 += a * __uint_as_float(av.x) + c * __uint_as_float(av.y);
      dt1 += d * __uint_as_float(av.x) + e * __uint_as_float(av.y);
    }
#pragma unroll
    for (int o2 = 1; o2 < 4; o2 <<= 1) {
      su0 += __shfl_xor_sync(0xffffffffu, su0, o2); su1 += __shfl_xor_sync(0xffffffffu, su1, o2);
      sq0 += __shfl_xor_sync(0xffffffffu, sq0, o2); sq1 += __shfl_xor_sync(0xffffffffu, sq1, o2);
      dt0 += __shfl_xor_sync(0xffffffffu, dt0, o2); dt1 += __shfl_xor_sync(0xffffffffu, dt1, o2);
    }
    if (tq < 2) st_b128(g_stats + ((size_t)cj * SEQ + grow0 + tq * 8) * 4, __float_as_uint(tq ? su1 : su0), __float_as_uint(tq ? sq1 : sq0), __float_as_uint(tq ? dt1 : dt0), tag);
    PROF(ct == 0, 29);
#pragma unroll
    for (int i = 0; i < 16; i += 2) stmatrix4((trow ^ ((i & 7) << 4)) + (i >> 3) * 16384, xr[2 * i], xr[2 * i + 1], xr[2 * i + 2], xr[2 * i + 3]);
    {
      const uint32_t* sp = g_stats + ((size_t)(2 * tq) * SEQ + grow0) * 4;
      uint4 v0 = ld_b128(sp), v1 = ld_b128(sp + SEQ * 4), v2 = ld_b128(sp + 32), v3 = ld_b128(sp + SEQ * 4 + 32);
      uint32_t n = 0;
      while (v0.w != tag || v1.w != tag || v2.w != tag || v3.w != tag) {
        if (v0.w != tag) v0 = ld_b128(sp);
        if (v1.w != tag) v1 = ld_b128(sp + SEQ * 4);
        if (v2.w != tag) v2 = ld_b128(sp + 32);
        if (v3.w != tag) v3 = ld_b128(sp + SEQ * 4 + 32);
        watchdog(n);
      }
      su0 = __uint_as_float(v0.x) + __uint_as_float(v1.x); sq0 = __uint_as_float(v0.y) + __uint_as_float(v1.y); dt0 = __uint_as_float(v0.z) + __uint_as_float(v1.z);
      su1 = __uint_as_float(v2.x) + __uint_as_float(v3.x); sq1 = __uint_as_float(v2.y) + __uint_as_float(v3.y); dt1 = __uint_as_float(v2.z) + __uint_as_float(v3.z);
    }
#pragma unroll
    for (int o2 = 1; o2 < 4; o2 <<= 1) {
      su0 += __shfl_xor_sync(0xffffffffu, su0, o2); su1 += __shfl_xor_sync(0xffffffffu, su1, o2);
      sq0 += __shfl_xor_sync(0xffffffffu, sq0, o2); sq1 += __shfl_xor_sync(0xffffffffu, sq1, o2);
      dt0 += __shfl_xor_sync(0xffffffffu, dt0, o2); dt1 += __shfl_xor_sync(0xffffffffu, dt1, o2);
    }
    PROF(ct == 0, 30);
    float mb0, sd0, mb1, sd1;
    {
      const float m0 = su0 * (1.f / DM), m1 = su1 * (1.f / DM);
      ln_scalars(m0, fmaxf(sq0 * (1.f / DM) - m0 * m0, 0.f), mb0, sd0);
      ln_scalars(m1, fmaxf(sq1 * (1.f / DM) - m1 * m1, 0.f), mb1, sd1);
    }
    const float inv0 = 1.f / sd0, inv1 = 1.f / sd1;
    uint32_t ih0, il0, ih1, il1;
    split_inv(sd0, ih0, il0);
    split_inv(sd1, ih1, il1);
    const uint4 cst = lds4(par + PAR_CONST);
    const float A1 = __uint_as_float(cst.x) + __uint_as_float(cst.z), A2 = __uint_as_float(cst.y) + __uint_as_float(cst.w);
    const float r0 = (dt0 - mb0 * A1) * inv0 + A2, r1 = (dt1 - mb1 * A1) * inv1 + A2;
    float rbest = r1 > r0 ? r1 : r0;
    int ibest = r1 > r0 ? lrow0 + 8 : lrow0;
#pragma unroll
    for (int o2 = 4; o2 < 32; o2 <<= 1) {
      const float ro = __shfl_xor_sync(0xffffffffu, rbest, o2);
      const int io = __shfl_xor_sync(0xffffffffu, ibest, o2);
      if (ro > rbest || (ro == rbest && io < ibest)) { rbest = ro; ibest = io; }
    }
    if (lane0) sts2(par + PAR_RED + warp * 8, __float_as_uint(rbest), ibest);
    PROF(ct == 0, 38);
    mbar_wait(bar_rst, 0);
    bar_sync(1, 256);
    PROF(ct == 0, 39);
    {
      const uint2 cv = lds2(par + PAR_RED + (ln & 7) * 8);
      rbest = __uint_as_float(cv.x); ibest = cv.y;
#pragma unroll
      for (int o2 = 1; o2 < 8; o2 <<= 1) {
        const float ro = __shfl_xor_sync(0xffffffffu, rbest, o2);
        const int io = __shfl_xor_sync(0xffffffffu, ibest, o2);
        if (ro > rbest || (ro == rbest && io < ibest)) { rbest = ro; ibest = io; }
      }
    }
    if (cj == 0 && ct == 0) st_relaxed2(g_cand + rb * 8, tagf(rbest, tag), ((rb * 128 + ibest) << 2) | tag);
    const uint32_t mm0 = pack_bf(mb0, mb0), mm1 = pack_bf(mb1, mb1);
    if ((ibest >> 4) == warp) {
      const bool hi = ibest & 8;
      const int src = (ibest & 7) * 4, ch = g * 2;
      const uint32_t mm = __shfl_sync(0xffffffffu, hi ? mm1 : mm0, src), ih = __shfl_sync(0xffffffffu, hi ? ih1 : ih0, src), il = __shfl_sync(0xffffffffu, hi ? il1 : il0, src);
      const uint32_t xa = res + (ch >> 3) * 16384 + ibest * 128 + (((ch & 7) ^ (ibest & 7)) << 4) + tq * 4;
      const uint32_t x0 = lds1(xa), x1 = lds1(xa ^ 16);
      const uint32_t pc = par + (8 * ch + 2 * tq) * 2;
      const uint32_t h0 = ln_mod(x0, mm, ih, il, lds1(pc + PAR_CB1), lds1(pc + PAR_SB)), h1 = ln_mod(x1, mm, ih, il, lds1(pc + PAR_CB1 + 16), lds1(pc + PAR_SB + 16));
      uint32_t* dst = g_row + rb * 2 * DM + cj * 128 + ln * 4;
      st_pairs(dst, h0, h1, tag);
      st_pairs(dst + DM, x0, x1, tag);
      __syncwarp();
    }
    uint32_t wf[128];
    const uint32_t frow = (ln & 7) + (ln >> 4) * 8;
    const uint32_t wfa = base + OFF_GATE + warp * 8192 + frow * 64 + ((((ln >> 3) & 1) ^ ((frow >> 1) & 3)) << 4);
#define LOAD_WF(f) ldmatrix4t((wfa ^ (((f) & 1) * 32)) + (((f) >> 1) & 1) * 4 * UNIT + ((f) >> 2) * 1024, wf[4 * (f)], wf[4 * (f) + 1], wf[4 * (f) + 2], wf[4 * (f) + 3])
    const bool early = __all_sync(0xffffffffu, b >= NFFN || mbar_test(bar_w1, 0));
    PROF(ct == 0, 37);
#pragma unroll
    for (int i = 0; i < 16; i += 2) {
      uint32_t ov[4];
      if (early) {
#pragma unroll
        for (int mt = 0; mt < 4; mt++) LOAD_WF(i * 2 + mt);
      }
#pragma unroll
      for (int u = 0; u < 2; u++) {
        const int ii = i + u;
        const uint32_t cb1 = lds1(par + PAR_CB1 + (8 * ii + 2 * tq) * 2), sb = lds1(par + PAR_SB + (8 * ii + 2 * tq) * 2);
        const uint32_t gb = lds1(par + PAR_GB + (8 * ii + 2 * tq) * 2);
        const uint32_t h0 = ln_mod(xr[2 * ii], mm0, ih0, il0, cb1, sb), h1 = ln_mod(xr[2 * ii + 1], mm1, ih1, il1, cb1, sb);
        ov[2 * u] = hadd2(xr[2 * ii], hmul2(gb, h0));
        ov[2 * u + 1] = hadd2(xr[2 * ii + 1], hmul2(gb, h1));
      }
      stmatrix4((trow ^ ((i & 7) << 4)) + (i >> 3) * 16384, ov[0], ov[1], ov[2], ov[3]);
    }
    PROF(ct == 0, 31);
    auto store_tile = [&](int skip) {
      const int wrow0 = wg * 64 + (warp & 3) * 16;
#pragma unroll
      for (int p = 0; p < 8; p++) {
        const int row = 2 * p + (ln >> 4), ch = ln & 15;
        const uint4 v = lds4(res + (ch >> 3) * 16384 + (wrow0 + row) * 128 + (((ch & 7) ^ (row & 7)) << 4));
        if (rb * 128 + wrow0 + row != skip) *reinterpret_cast<uint4*>(P.out + (size_t)(rb * 128 + wrow0 + row) * DM + cj * 128 + ch * 8) = v;
      }
    };
    uint2 cv = ld_relaxed2(g_cand + (ln & 15) * 8);
    if (!early) {
      mbar_wait(bar_w1, 0);
#pragma unroll
      for (int f = 0; f < 32; f++) LOAD_WF(f);
    }
    float rwin; int iwin;
    uint4 hv[8];
    uint32_t wd[64];
    const uint32_t wda = base + warp * 8192 + frow * 128 + ((((ln >> 3) & 1) ^ (ln & 7)) << 4);
#define LOAD_WD(f) ldmatrix4t((wda ^ ((((f) >> 1) & 3) * 32)) + ((f) >> 3) * 4096 + ((f) & 1) * 2048, wd[4 * (f)], wd[4 * (f) + 1], wd[4 * (f) + 2], wd[4 * (f) + 3])
    {
      uint32_t n = 0;
      int cur = -1;
      while (true) {
        const bool valid = !(((cv.x ^ tag) | (cv.y ^ tag)) & 3u);
        const uint32_t bits = cv.x & ~3u;
        const uint32_t key = valid ? ((int)bits < 0 ? ~bits : bits | 0x80000000u) : 0u;
        const uint32_t best = __reduce_max_sync(0xffffffffu, key);
        const int src = (__ffs(__ballot_sync(0xffffffffu, key == best)) - 1) & 15;
        if (best && src != cur) {
          cur = src;
#pragma unroll
          for (int i = 0; i < 8; i++) hv[i] = ld_pairs(g_row + cur * 2 * DM + warp * 128 + i * 16 + tq * 4);
        }
        if (__all_sync(0xffffffffu, valid)) break;
        if (!valid) cv = ld_relaxed2(g_cand + (ln & 15) * 8);
        watchdog(n);
      }
      rwin = __uint_as_float(__shfl_sync(0xffffffffu, cv.x, cur) & ~3u);
      iwin = __shfl_sync(0xffffffffu, cv.y, cur) >> 2;
    }
    PROF(ct == 0, 32);
    const uint32_t* wrow = g_row + (iwin >> 7) * 2 * DM;
    if (b < NFFN) {
      {
        uint32_t n = 0;
        bool ok;
        do {
          ok = true;
#pragma unroll
          for (int i = 0; i < 8; i++)
            if (hv[i].y != tag || hv[i].w != tag) { hv[i] = ld_pairs(wrow + warp * 128 + i * 16 + tq * 4); ok = false; }
          watchdog(n);
        } while (!ok);
      }
      __syncwarp();
      PROF(ct == 0, 33);
      float d[8][4];
#pragma unroll
      for (int i = 0; i < 8; i++) { d[i][0] = 0.f; d[i][1] = 0.f; d[i][2] = 0.f; d[i][3] = 0.f; }
#pragma unroll
      for (int ks = 0; ks < 8; ks++) {
#pragma unroll
        for (int mt = 0; mt < 4; mt++) {
          const int r = ks * 16 + mt * 4;
          mma16816(d[mt + (ks & 1) * 4], wf[r], wf[r + 1], wf[r + 2], wf[r + 3], hv[ks].x, hv[ks].z);
        }
        if (ks == 1) mbar_wait(bar_w2, 0);
        if (ks >= 1) {
#pragma unroll
          for (int f = 4 * ks - 4; f < 16 && f < 4 * ks; f++) LOAD_WD(f);
        }
      }
      const uint32_t red = base + OFF_GATE;
      if (tq == 0) {
        const uint32_t dst = red + warp * 8192 + g * 32;
        sts4(dst, make_uint4(__float_as_uint(d[0][0] + d[4][0]), __float_as_uint(d[0][2] + d[4][2]), __float_as_uint(d[1][0] + d[5][0]), __float_as_uint(d[1][2] + d[5][2])));
        sts4(dst + 16, make_uint4(__float_as_uint(d[2][0] + d[6][0]), __float_as_uint(d[2][2] + d[6][2]), __float_as_uint(d[3][0] + d[7][0]), __float_as_uint(d[3][2] + d[7][2])));
      }
      bar_sync(1, 256);
      uint32_t ab[4];
      {
        float G = 0.f, U = 0.f;
        const uint32_t src = red + (ln & 7) * 32 + (ln >> 3) * 4;
#pragma unroll
        for (int w8 = 0; w8 < 8; w8++) { G += __uint_as_float(lds1(src + w8 * 8192)); U += __uint_as_float(lds1(src + w8 * 8192 + 16)); }
        const float act = rbf(silu_f(rbf(G))) * rbf(U);
        const uint32_t pk = pack_bf(act, __shfl_down_sync(0xffffffffu, act, 1));
#pragma unroll
        for (int i = 0; i < 4; i++) ab[i] = __shfl_sync(0xffffffffu, pk, i * 8 + tq * 2);
      }
      PROF(ct == 0, 34);
#pragma unroll
      for (int mt = 0; mt < 8; mt++) {
        d[mt][0] = 0.f; d[mt][1] = 0.f; d[mt][2] = 0.f; d[mt][3] = 0.f;
        mma16816(d[mt], wd[mt * 8], wd[mt * 8 + 1], wd[mt * 8 + 2], wd[mt * 8 + 3], ab[0], ab[1]);
        mma16816(d[mt], wd[mt * 8 + 4], wd[mt * 8 + 5], wd[mt * 8 + 6], wd[mt * 8 + 7], ab[2], ab[3]);
      }
#pragma unroll
      for (int i = 0; i < 4; i++) {
        const int m4 = (i >> 1) * 4, e = (i & 1) * 2;
        const float y = (tq & 2) ? ((tq & 1) ? d[m4 + 3][e] : d[m4 + 2][e]) : ((tq & 1) ? d[m4 + 1][e] : d[m4][e]);
        st_relaxed(g_ypart + ((size_t)(warp * 16 + (m4 + tq) * 2 + (i & 1)) * NFFN + b) * 8 + g, tagf(y, tag));
      }
      PROF(ct == 0, 35);
    }
    store_tile(iwin);
    {
      uint2 fh = make_uint2(0, 0), fx = make_uint2(0, 0);
      const uint32_t* src = wrow + (b >> 1) * 16 + (ct & 3) * 4 + (b & 1) * 2;
      if (ct < 4) { fh = ld_pair(src); fx = ld_pair(src + DM); }
      float y0 = 0.f, y1 = 0.f, y2 = 0.f, y3 = 0.f;
      if (ct < 2 * NFFN) {
        const uint4 v = poll4(g_ypart + (size_t)b * NFFN * 8 + ct * 4, tag);
        y0 = __uint_as_float(v.x & ~3u); y1 = __uint_as_float(v.y & ~3u); y2 = __uint_as_float(v.z & ~3u); y3 = __uint_as_float(v.w & ~3u);
      }
      __syncwarp();
      PROF(ct == 0, 5); PROF(ct == 96, 11); PROF(ct == 192, 12);
      if (ct < 4) {
        uint32_t n = 0;
        while (fh.y != tag || fx.y != tag) { fh = ld_pair(src); fx = ld_pair(src + DM); watchdog(n); }
      }
#pragma unroll
      for (int o2 = 2; o2 < 32; o2 <<= 1) {
        y0 += __shfl_xor_sync(0xffffffffu, y0, o2); y1 += __shfl_xor_sync(0xffffffffu, y1, o2);
        y2 += __shfl_xor_sync(0xffffffffu, y2, o2); y3 += __shfl_xor_sync(0xffffffffu, y3, o2);
      }
      if (ln < 2) sts4(par + PAR_RED + 64 + warp * 32 + ln * 16, make_uint4(__float_as_uint(y0), __float_as_uint(y1), __float_as_uint(y2), __float_as_uint(y3)));
      PROF(ct == 0, 6);
      bar_sync(1, 256);
      PROF(ct == 0, 7);
      if (ct < 4) {
        float ya = 0.f, yb = 0.f;
#pragma unroll
        for (int w8 = 0; w8 < 7; w8++) {
          const uint2 v = lds2(par + PAR_RED + 64 + w8 * 32 + ct * 8);
          ya += __uint_as_float(v.x); yb += __uint_as_float(v.y);
        }
        const float rs = rbf(1.f / (1.f + __expf(-rbf(rwin))));
        const uint2 gv = lds2(par + PAR_CONST + 16 + ct * 8);
        const uint32_t upd = hmul2(pack_bf(ya, yb), pack_bf(rs, rs));
        *reinterpret_cast<uint32_t*>(P.out + (size_t)iwin * DM + b * 8 + ct * 2) =
            hadd2(fx.x, hmul2(__byte_perm(gv.x, gv.y, 0x7632), hadd2(fh.x, upd)));
      }
      if (b == 0 && ct == 0) st_relaxed(&g_epoch, lds1(par + PAR_CONST + 48) + 1);
    }
    PROF(ct == 0, 36);
    cluster_wait();
  }
}

typedef CUresult (*EncodeFn)(CUtensorMap*, CUtensorMapDataType, cuuint32_t, void*, const cuuint64_t*, const cuuint64_t*,
                             const cuuint32_t*, const cuuint32_t*, CUtensorMapInterleave, CUtensorMapSwizzle,
                             CUtensorMapL2promotion, CUtensorMapFloatOOBfill);

void map2d(EncodeFn enc, CUtensorMap* m, const void* p, uint64_t rows, uint64_t cols, uint32_t brows) {
  cuuint64_t dims[2] = {cols, rows}, strides[1] = {cols * 2};
  cuuint32_t box[2] = {64, brows}, es[2] = {1, 1};
  enc(m, CU_TENSOR_MAP_DATA_TYPE_BFLOAT16, 2, const_cast<void*>(p), dims, strides, box, es, CU_TENSOR_MAP_INTERLEAVE_NONE,
      CU_TENSOR_MAP_SWIZZLE_128B, CU_TENSOR_MAP_L2_PROMOTION_L2_256B, CU_TENSOR_MAP_FLOAT_OOB_FILL_NONE);
}
void map2d_narrow(EncodeFn enc, CUtensorMap* m, const void* p, uint64_t rows, uint64_t cols) {
  cuuint64_t dims[2] = {cols, rows}, strides[1] = {cols * 2};
  cuuint32_t box[2] = {32, 256}, es[2] = {1, 1};
  enc(m, CU_TENSOR_MAP_DATA_TYPE_BFLOAT16, 2, const_cast<void*>(p), dims, strides, box, es, CU_TENSOR_MAP_INTERLEAVE_NONE,
      CU_TENSOR_MAP_SWIZZLE_64B, CU_TENSOR_MAP_L2_PROMOTION_L2_64B, CU_TENSOR_MAP_FLOAT_OOB_FILL_NONE);
}
void map3d(EncodeFn enc, CUtensorMap* m, const void* p, uint64_t rows, uint64_t cols, uint32_t brows, uint32_t nch) {
  cuuint64_t dims[3] = {64, rows, cols / 64}, strides[2] = {cols * 2, 128};
  cuuint32_t box[3] = {64, brows, nch}, es[3] = {1, 1, 1};
  enc(m, CU_TENSOR_MAP_DATA_TYPE_BFLOAT16, 3, const_cast<void*>(p), dims, strides, box, es, CU_TENSOR_MAP_INTERLEAVE_NONE,
      CU_TENSOR_MAP_SWIZZLE_128B, CU_TENSOR_MAP_L2_PROMOTION_L2_256B, CU_TENSOR_MAP_FLOAT_OOB_FILL_NONE);
}

}

extern "C" void kernel_launch(void* const* d_in, const int* in_sizes, int n_in, void* d_out, int out_size) {
  (void)in_sizes; (void)n_in; (void)out_size;
  static EncodeFn enc = nullptr;
  if (!enc) {
    void* fn = nullptr;
    cudaDriverEntryPointQueryResult st;
    cudaGetDriverEntryPoint("cuTensorMapEncodeTiled", &fn, cudaEnableDefault, &st);
    enc = (EncodeFn)fn;
    cudaFuncSetAttribute(fused_kernel, cudaFuncAttributeMaxDynamicSharedMemorySize, SMEM_BYTES);
  }
  Maps maps;
  map2d(enc, &maps.x, d_in[0], SEQ, DM, 128);
  map3d(enc, &maps.wq, d_in[3], DM, NQ, 64, 2);
  map3d(enc, &maps.k, d_in[1], 4 * SK, 128, 128, 1);
  map3d(enc, &maps.v, d_in[2], 4 * SK, 128, 128, 1);
  map3d(enc, &maps.wo, d_in[4], NQ, DM, 64, 2);
  map2d_narrow(enc, &maps.wg, d_in[7], DM, FF);
  map2d_narrow(enc, &maps.wu, d_in[8], DM, FF);
  map3d(enc, &maps.wd, d_in[9], FF, DM, 32, 4);
  map2d_narrow(enc, &maps.wm, d_in[11], DM, NMOD);
  Ptrs p;
  p.x = (const __nv_bfloat16*)d_in[0];
  p.w_r = (const __nv_bfloat16*)d_in[6];
  p.w_gate = (const __nv_bfloat16*)d_in[7];
  p.w_up = (const __nv_bfloat16*)d_in[8];
  p.w_down = (const __nv_bfloat16*)d_in[9];
  p.c = (const __nv_bfloat16*)d_in[10];
  p.w_mod = (const __nv_bfloat16*)d_in[11];
  p.out = (__nv_bfloat16*)d_out;
  fused_kernel<<<NMAIN + NHELP, 384, SMEM_BYTES>>>(maps, p);
}
```

```cpp
#include <cuda_runtime.h>
#include <cuda_bf16.h>
#include <cuda.h>
#include <stdint.h>
#include <type_traits>

#define HD 1
#define HDX 2
#define XF 4
#define XE 32
#define XR 16
#define PF2 2
#define PF2T 2
#define NRS 6
#define FPACE 2
#define GOST 24
#define WB 2
#define WN 16
#define RES0 17
#define RES1 20
#define VREL 7
#define E0 3

namespace {

constexpr int SEQ = 2048, DM = 1024, NQ = 4096, SK = 2048, WIN = 512, FF = 3584, NMOD = 6144;
constexpr int NMAIN = 128, NHELP = 4, NFFN = 112;
constexpr int NSLOT = 4, SLOT_BYTES = 32768, UNIT = 16384, GST_BYTES = 3 * UNIT;
constexpr uint32_t XT0 = 0x9630, XT1 = 0x54DC, XT2 = 0xDC96;
constexpr uint32_t WT0 = 0xA741, WT1 = 0x720A, WT2 = 0x20A7;
constexpr uint32_t AT0 = 0x7420, AT1 = 0x2C0A;
constexpr uint32_t QT = 0x549696DC;
constexpr int OFF_STAGE = 12 * UNIT;
constexpr int OFF_RES = 4 * UNIT, OFF_GATE = 6 * UNIT;
constexpr int OFF_PAR = 14 * UNIT;
constexpr int OFF_BAR = OFF_PAR + 2048 + 512;
constexpr int SMEM_BYTES = OFF_BAR + 512;
static_assert(SMEM_BYTES <= 232448, "smem");

constexpr int PAR_GA = 0, PAR_CB1 = 256, PAR_SB = 512, PAR_GB = 768;
constexpr int PAR_A = 1024;
constexpr int PAR_CONST = 1536;
constexpr int PAR_RED = 1600;
constexpr int PAR_SINK = 2176;

struct Maps {
  CUtensorMap x, wq, k, v, wo, wg, wu, wd, wm;
};
struct Ptrs {
  const __nv_bfloat16 *x, *w_r, *c, *w_mod, *w_gate, *w_up, *w_down;
  __nv_bfloat16* out;
};

__device__ __align__(1024) uint8_t g_act[16 * 80 * UNIT];
__device__ __align__(128) uint32_t g_mod[NMOD];
__device__ __align__(128) uint32_t g_modp[2 * 2 * DM];
__device__ __align__(128) uint32_t g_ln1[SEQ * 4];
__device__ __align__(128) uint32_t g_cnt_h[16 * 32];
__device__ __align__(128) uint32_t g_cnt_o[128 * 32];
__device__ __align__(128) uint32_t g_xch[NMAIN * 8 * 256 * 4];
__device__ __align__(128) uint32_t g_stats[8 * SEQ * 4];
__device__ __align__(128) uint32_t g_cand[16 * 8];
__device__ __align__(128) uint32_t g_row[16 * 2 * DM];
__device__ __align__(128) uint32_t g_ypart[NMAIN * NFFN * 8];
__device__ uint32_t g_epoch;

__device__ __forceinline__ uint32_t fresh_lane() { uint32_t l; asm volatile("mov.u32 %0, %%laneid;" : "=r"(l)); return l; }
__device__ __forceinline__ uint32_t frag_offset(int warp) {
  const uint32_t l = fresh_lane();
  return ((warp & 3) * 16 + (l & 15)) * 128 + (((l >> 4) ^ (l & 7)) << 4);
}
__device__ __forceinline__ uint32_t smem_u32(const void* p) { return (uint32_t)__cvta_generic_to_shared(p); }
__device__ __forceinline__ void mbar_init(uint32_t bar, uint32_t cnt) {
  asm volatile("mbarrier.init.shared::cta.b64 [%0], %1;" ::"r"(bar), "r"(cnt) : "memory");
}
__device__ __forceinline__ void mbar_expect_tx(uint32_t bar, uint32_t bytes) {
  asm volatile("mbarrier.arrive.expect_tx.shared::cta.b64 _, [%0], %1;" ::"r"(bar), "r"(bytes) : "memory");
}
__device__ __forceinline__ void mbar_arrive(uint32_t bar) {
  asm volatile("mbarrier.arrive.shared::cta.b64 _, [%0];" ::"r"(bar) : "memory");
}
__device__ __forceinline__ void mbar_arrive_pred(uint32_t bar, bool p) {
  asm volatile("{ .reg .pred p; setp.ne.b32 p, %1, 0; @p mbarrier.arrive.shared::cta.b64 _, [%0]; }" ::"r"(bar), "r"((int)p) : "memory");
}
__device__ __forceinline__ void mbar_arrive_cl(uint32_t bar, uint32_t off, bool p = true) {
  asm volatile("{ .reg .pred p, q; .reg .b32 a; setp.ne.b32 q, %2, 0; setp.ne.and.b32 p, %0, 0, q; add.u32 a, %0, %1; @p mbarrier.arrive.shared::cluster.b64 _, [a]; }"
               ::"r"(bar), "r"(off), "r"((int)p) : "memory");
}
__device__ __forceinline__ uint32_t mapa(uint32_t addr, uint32_t cta) {
  uint32_t r; asm("mapa.shared::cluster.u32 %0, %1, %2;" : "=r"(r) : "r"(addr), "r"(cta)); return r;
}
__device__ __forceinline__ void cluster_arrive() { asm volatile("barrier.cluster.arrive.relaxed.aligned;" ::: "memory"); }
__device__ __forceinline__ void cluster_wait() { asm volatile("barrier.cluster.wait.aligned;" ::: "memory"); }
__device__ __forceinline__ void watchdog(uint32_t& n) {
  asm volatile("{\n.reg .pred q;\n.reg .u64 z;\nadd.u32 %0, %0, 1;\nsetp.gt.u32 q, %0, 0x1000000;\nmov.u64 z, 0;\n@q st.global.u32 [z], %0;\n}" : "+r"(n)::"memory");
}
__device__ __forceinline__ void mbar_wait(uint32_t bar, uint32_t parity) {
  asm volatile(
      "{\n.reg .pred p, q;\n.reg .u32 n;\n.reg .u64 z;\nmov.u32 n, 0;\nmov.u64 z, 0;\n"
      "WAIT_%=:\n"
      "mbarrier.try_wait.parity.shared::cta.b64 p, [%0], %1;\n"
      "@p bra DONE_%=;\n"
      "add.u32 n, n, 1;\n"
      "setp.gt.u32 q, n, 0x400000;\n"
      "@q st.global.u32 [z], n;\n"
      "bra WAIT_%=;\n"
      "DONE_%=:\n}" ::"r"(bar), "r"(parity) : "memory");
}
__device__ __forceinline__ bool mbar_test(uint32_t bar, uint32_t parity) {
  uint32_t ok;
  asm volatile("{\n.reg .pred p;\nmbarrier.test_wait.parity.shared::cta.b64 p, [%1], %2;\nselp.u32 %0, 1, 0, p;\n}" : "=r"(ok) : "r"(bar), "r"(parity) : "memory");
  return ok;
}
__device__ __forceinline__ uint64_t l2_stream() {
  uint64_t f; asm("createpolicy.fractional.L2::evict_first.b64 %0, 1.0;" : "=l"(f)); return f;
}
__device__ __forceinline__ void tma2d(uint32_t dst, const CUtensorMap* m, int c0, int c1, uint32_t bar) {
  asm volatile("cp.async.bulk.tensor.2d.shared::cluster.global.mbarrier::complete_tx::bytes.L2::cache_hint [%0], [%1, {%3, %4}], [%2], %5;"
               ::"r"(dst), "l"(m), "r"(bar), "r"(c0), "r"(c1), "l"(l2_stream()) : "memory");
}
__device__ __forceinline__ void tma3d_prefetch(const CUtensorMap* m, int c0, int c1, int c2) {
  asm volatile("cp.async.bulk.prefetch.tensor.3d.L2.global.tile [%0, {%1, %2, %3}];" ::"l"(m), "r"(c0), "r"(c1), "r"(c2) : "memory");
}
__device__ __forceinline__ void bulk_load(uint32_t dst, const void* src, uint32_t bytes, uint32_t bar) {
  asm volatile("cp.async.bulk.shared::cluster.global.mbarrier::complete_tx::bytes [%0], [%1], %2, [%3];" ::"r"(dst), "l"(src), "r"(bytes), "r"(bar) : "memory");
}
__device__ __forceinline__ void bulk_load_stream(uint32_t dst, const void* src, uint32_t bytes, uint32_t bar) {
  asm volatile("cp.async.bulk.shared::cluster.global.mbarrier::complete_tx::bytes.L2::cache_hint [%0], [%1], %2, [%3], %4;"
               ::"r"(dst), "l"(src), "r"(bytes), "r"(bar), "l"(l2_stream()) : "memory");
}
__device__ __forceinline__ void bulk_store(void* dst, uint32_t src, uint32_t bytes) {
  asm volatile("cp.async.bulk.global.shared::cta.bulk_group [%0], [%1], %2;" ::"l"(dst), "r"(src), "r"(bytes) : "memory");
}
__device__ __forceinline__ uint32_t unit_of(uint32_t table, uint32_t i) { return ((table >> (i * 4)) & 15) * UNIT; }
__device__ __forceinline__ void tma3d(uint32_t dst, const CUtensorMap* m, int c0, int c1, int c2, uint32_t bar) {
  asm volatile("cp.async.bulk.tensor.3d.shared::cluster.global.mbarrier::complete_tx::bytes.L2::cache_hint [%0], [%1, {%3, %4, %5}], [%2], %6;"
               ::"r"(dst), "l"(m), "r"(bar), "r"(c0), "r"(c1), "r"(c2), "l"(l2_stream()) : "memory");
}
template <bool STREAM>
__device__ __forceinline__ void tma3d_mc(uint32_t dst, const CUtensorMap* m, int c0, int c1, int c2, uint32_t bar) {
  if (STREAM)
    asm volatile("cp.async.bulk.tensor.3d.shared::cluster.global.mbarrier::complete_tx::bytes.multicast::cluster.L2::cache_hint [%0], [%1, {%3, %4, %5}], [%2], %6, %7;"
                 ::"r"(dst), "l"(m), "r"(bar), "r"(c0), "r"(c1), "r"(c2), "h"((uint16_t)3), "l"(l2_stream()) : "memory");
  else
    asm volatile("cp.async.bulk.tensor.3d.shared::cluster.global.mbarrier::complete_tx::bytes.multicast::cluster [%0], [%1, {%3, %4, %5}], [%2], %6;"
                 ::"r"(dst), "l"(m), "r"(bar), "r"(c0), "r"(c1), "r"(c2), "h"((uint16_t)3) : "memory");
}
__device__ __forceinline__ void prefetch_map(const CUtensorMap* m) {
  asm volatile("prefetch.tensormap [%0];" ::"l"(m) : "memory");
}
__device__ __forceinline__ void fence_async() { asm volatile("fence.proxy.async.global;" ::: "memory"); }
__device__ __forceinline__ void fence_async_smem() { asm volatile("fence.proxy.async.shared::cta;" ::: "memory"); }
__device__ __forceinline__ void bar_sync(int id, int n) { asm volatile("bar.sync %0, %1;" ::"r"(id), "r"(n) : "memory"); }
__device__ __forceinline__ void bar_arrive(int id, int n) { asm volatile("bar.arrive %0, %1;" ::"r"(id), "r"(n) : "memory"); }
__device__ __forceinline__ void wg_fence() { asm volatile("wgmma.fence.sync.aligned;" ::: "memory"); }
__device__ __forceinline__ void wg_commit() { asm volatile("wgmma.commit_group.sync.aligned;" ::: "memory"); }
template <int N> __device__ __forceinline__ void wg_wait() { asm volatile("wgmma.wait_group.sync.aligned %0;" ::"n"(N) : "memory"); }
__device__ __forceinline__ uint64_t make_desc(uint32_t addr, uint32_t lbo, uint32_t sbo) {
  return (uint64_t)((addr & 0x3FFFF) >> 4) | ((uint64_t)(lbo >> 4) << 16) | ((uint64_t)(sbo >> 4) << 32) | (1ull << 62);
}
__device__ __forceinline__ uint32_t ld_relaxed(const uint32_t* p) {
  uint32_t v; asm volatile("ld.relaxed.gpu.global.u32 %0, [%1];" : "=r"(v) : "l"(p) : "memory"); return v;
}
__device__ __forceinline__ uint32_t ld_acquire(const uint32_t* p) {
  uint32_t v; asm volatile("ld.acquire.gpu.global.u32 %0, [%1];" : "=r"(v) : "l"(p) : "memory"); return v;
}
__device__ __forceinline__ uint4 ld_relaxed4(const uint32_t* p) {
  uint4 v; asm volatile("ld.relaxed.gpu.global.v4.u32 {%0,%1,%2,%3}, [%4];" : "=r"(v.x), "=r"(v.y), "=r"(v.z), "=r"(v.w) : "l"(p) : "memory"); return v;
}
__device__ __forceinline__ uint2 ld_relaxed2(const uint32_t* p) {
  uint2 v; asm volatile("ld.relaxed.gpu.global.v2.u32 {%0,%1}, [%2];" : "=r"(v.x), "=r"(v.y) : "l"(p) : "memory"); return v;
}
__device__ __forceinline__ void st_relaxed(uint32_t* p, uint32_t v) {
  asm volatile("st.relaxed.gpu.global.u32 [%0], %1;" ::"l"(p), "r"(v) : "memory");
}
__device__ __forceinline__ void st_relaxed2(uint32_t* p, uint32_t a, uint32_t b) {
  asm volatile("st.relaxed.gpu.global.v2.u32 [%0], {%1,%2};" ::"l"(p), "r"(a), "r"(b) : "memory");
}
__device__ __forceinline__ void st_relaxed4(uint32_t* p, uint32_t a, uint32_t b, uint32_t c, uint32_t d) {
  asm volatile("st.relaxed.gpu.global.v4.u32 [%0], {%1,%2,%3,%4};" ::"l"(p), "r"(a), "r"(b), "r"(c), "r"(d) : "memory");
}
__device__ __forceinline__ void st_b128(uint32_t* p, uint32_t a, uint32_t b, uint32_t c, uint32_t d) {
  asm volatile("{ .reg .b64 u, v; .reg .b128 w; mov.b64 u, {%1, %2}; mov.b64 v, {%3, %4}; mov.b128 w, {u, v}; st.relaxed.gpu.global.b128 [%0], w; }"
               ::"l"(p), "r"(a), "r"(b), "r"(c), "r"(d) : "memory");
}
__device__ __forceinline__ uint4 ld_b128(const uint32_t* p) {
  uint4 r;
  asm volatile("{ .reg .b64 u, v; .reg .b128 w; ld.relaxed.gpu.global.b128 w, [%4]; mov.b128 {u, v}, w; mov.b64 {%0, %1}, u; mov.b64 {%2, %3}, v; }"
               : "=r"(r.x), "=r"(r.y), "=r"(r.z), "=r"(r.w) : "l"(p) : "memory");
  return r;
}
__device__ __forceinline__ void st_pairs(uint32_t* p, uint32_t a, uint32_t b, uint32_t tag) {
  asm volatile("{ .reg .b64 u, v; mov.b64 u, {%1, %3}; mov.b64 v, {%2, %3}; st.relaxed.gpu.global.v2.b64 [%0], {u, v}; }"
               ::"l"(p), "r"(a), "r"(b), "r"(tag) : "memory");
}
__device__ __forceinline__ uint4 ld_pairs(const uint32_t* p) {
  uint4 v;
  asm volatile("{ .reg .b64 u, v; ld.relaxed.gpu.global.v2.b64 {u, v}, [%4]; mov.b64 {%0, %1}, u; mov.b64 {%2, %3}, v; }"
               : "=r"(v.x), "=r"(v.y), "=r"(v.z), "=r"(v.w) : "l"(p) : "memory");
  return v;
}
__device__ __forceinline__ uint2 ld_pair(const uint32_t* p) {
  uint2 v;
  asm volatile("{ .reg .b64 u; ld.relaxed.gpu.global.b64 u, [%2]; mov.b64 {%0, %1}, u; }" : "=r"(v.x), "=r"(v.y) : "l"(p) : "memory");
  return v;
}
__device__ __forceinline__ void red_release(uint32_t* p, uint32_t v) {
  asm volatile("red.release.gpu.global.add.u32 [%0], %1;" ::"l"(p), "r"(v) : "memory");
}
__device__ __forceinline__ uint32_t ldg_nc1(const void* p) {
  uint32_t v;
  asm volatile("ld.global.nc.u32 %0, [%1];" : "=r"(v) : "l"(p));
  return v;
}
__device__ __forceinline__ uint4 ldg_nc4(const void* p) {
  uint4 v; asm volatile("ld.global.nc.L1::no_allocate.v4.u32 {%0,%1,%2,%3}, [%4];" : "=r"(v.x), "=r"(v.y), "=r"(v.z), "=r"(v.w) : "l"(p)); return v;
}
__device__ __forceinline__ void stg4(void* p, uint4 v) {
  asm volatile("st.global.v4.u32 [%0], {%1,%2,%3,%4};" ::"l"(p), "r"(v.x), "r"(v.y), "r"(v.z), "r"(v.w) : "memory");
}
__device__ __forceinline__ void wait_counter(const uint32_t* p, uint32_t target) {
  uint32_t n = 0;
  while ((int)(ld_acquire(p) - target) < 0) { watchdog(n); }
}
__device__ __forceinline__ uint32_t tagf(float v, uint32_t tag) { return (__float_as_uint(v) & ~3u) | tag; }
__device__ __forceinline__ bool tag_ok(uint4 v, uint32_t tag) { return (((v.x ^ tag) | (v.y ^ tag) | (v.z ^ tag) | (v.w ^ tag)) & 3u) == 0; }
__device__ __forceinline__ float untag_sum(uint32_t a, uint32_t b) { return __uint_as_float(a & ~3u) + __uint_as_float(b & ~3u); }
__device__ __forceinline__ uint4 poll4(const uint32_t* p, uint32_t tag) {
  uint4 v = ld_relaxed4(p);
  uint32_t n = 0;
  while (!tag_ok(v, tag)) { v = ld_relaxed4(p); watchdog(n); }
  return v;
}
__device__ __forceinline__ float bf_lo(uint32_t v) { return __uint_as_float(v << 16); }
__device__ __forceinline__ float bf_hi(uint32_t v) { return __uint_as_float(v & 0xffff0000u); }
__device__ __forceinline__ uint32_t pack_bf(float lo, float hi) {
  uint32_t r; asm("cvt.rn.bf16x2.f32 %0, %1, %2;" : "=r"(r) : "f"(hi), "f"(lo)); return r;
}
__device__ __forceinline__ float rbf(float v) { return __uint_as_float(pack_bf(0.f, v) & 0xffff0000u); }
__device__ __forceinline__ uint32_t hmul2(uint32_t a, uint32_t b) {
  uint32_t r; asm("mul.rn.bf16x2 %0, %1, %2;" : "=r"(r) : "r"(a), "r"(b)); return r;
}
__device__ __forceinline__ uint32_t hadd2(uint32_t a, uint32_t b) {
  uint32_t r; asm("add.rn.bf16x2 %0, %1, %2;" : "=r"(r) : "r"(a), "r"(b)); return r;
}
__device__ __forceinline__ uint32_t hsub2(uint32_t a, uint32_t b) {
  uint32_t r; asm("sub.rn.bf16x2 %0, %1, %2;" : "=r"(r) : "r"(a), "r"(b)); return r;
}
__device__ __forceinline__ uint32_t hmax2(uint32_t a, uint32_t b) {
  uint32_t r; asm("max.bf16x2 %0, %1, %2;" : "=r"(r) : "r"(a), "r"(b)); return r;
}
__device__ __forceinline__ float ex2(float x) { float r; asm("ex2.approx.ftz.f32 %0, %1;" : "=f"(r) : "f"(x)); return r; }
__device__ __forceinline__ void stmatrix4(uint32_t addr, uint32_t a, uint32_t b, uint32_t c, uint32_t d) {
  asm volatile("stmatrix.sync.aligned.m8n8.x4.shared.b16 [%0], {%1,%2,%3,%4};" ::"r"(addr), "r"(a), "r"(b), "r"(c), "r"(d) : "memory");
}
__device__ __forceinline__ void ldmatrix4(uint32_t addr, uint32_t& a, uint32_t& b, uint32_t& c, uint32_t& d) {
  asm volatile("ldmatrix.sync.aligned.m8n8.x4.shared.b16 {%0,%1,%2,%3}, [%4];" : "=r"(a), "=r"(b), "=r"(c), "=r"(d) : "r"(addr) : "memory");
}
__device__ __forceinline__ void ldmatrix4t(uint32_t addr, uint32_t& a, uint32_t& b, uint32_t& c, uint32_t& d) {
  asm volatile("ldmatrix.sync.aligned.m8n8.x4.trans.shared.b16 {%0,%1,%2,%3}, [%4];" : "=r"(a), "=r"(b), "=r"(c), "=r"(d) : "r"(addr) : "memory");
}
__device__ __forceinline__ void mma16816(float (&d)[4], uint32_t a0, uint32_t a1, uint32_t a2, uint32_t a3, uint32_t b0, uint32_t b1) {
  asm volatile("mma.sync.aligned.m16n8k16.row.col.f32.bf16.bf16.f32 {%0,%1,%2,%3}, {%4,%5,%6,%7}, {%8,%9}, {%0,%1,%2,%3};"
               : "+f"(d[0]), "+f"(d[1]), "+f"(d[2]), "+f"(d[3]) : "r"(a0), "r"(a1), "r"(a2), "r"(a3), "r"(b0), "r"(b1));
}
__device__ __forceinline__ void sts1(uint32_t a, uint32_t v) { asm volatile("st.shared.u32 [%0], %1;" ::"r"(a), "r"(v) : "memory"); }
__device__ __forceinline__ uint4 lds4(uint32_t a) {
  uint4 v; asm volatile("ld.shared.v4.u32 {%0,%1,%2,%3}, [%4];" : "=r"(v.x), "=r"(v.y), "=r"(v.z), "=r"(v.w) : "r"(a) : "memory"); return v;
}
__device__ __forceinline__ uint2 lds2(uint32_t a) {
  uint2 v; asm volatile("ld.shared.v2.u32 {%0,%1}, [%2];" : "=r"(v.x), "=r"(v.y) : "r"(a) : "memory"); return v;
}
__device__ __forceinline__ uint32_t lds1(uint32_t a) {
  uint32_t v; asm volatile("ld.shared.u32 %0, [%1];" : "=r"(v) : "r"(a) : "memory"); return v;
}
__device__ __forceinline__ void sts2(uint32_t a, uint32_t x, uint32_t y) { asm volatile("st.shared.v2.u32 [%0], {%1,%2};" ::"r"(a), "r"(x), "r"(y) : "memory"); }
__device__ __forceinline__ void sts4(uint32_t a, uint4 v) {
  asm volatile("st.shared.v4.u32 [%0], {%1,%2,%3,%4};" ::"r"(a), "r"(v.x), "r"(v.y), "r"(v.z), "r"(v.w) : "memory");
}
__device__ __forceinline__ float silu_f(float v) { return __fdividef(v, 1.f + __expf(-v)); }
__device__ __forceinline__ uint32_t hfma2(uint32_t a, uint32_t b, uint32_t c) {
  uint32_t r; asm("fma.rn.bf16x2 %0, %1, %2, %3;" : "=r"(r) : "r"(a), "r"(b), "r"(c)); return r;
}
__device__ __forceinline__ void split_inv(float sd, uint32_t& ih, uint32_t& il) {
  const float inv = 1.f / sd;
  ih = pack_bf(inv, inv);
  const float lo = inv - bf_lo(ih);
  il = pack_bf(lo, lo);
}
__device__ __forceinline__ uint32_t ln_mod(uint32_t x, uint32_t mean2, uint32_t ih, uint32_t il, uint32_t c1, uint32_t sh) {
  const uint32_t d = hsub2(x, mean2);
  return hadd2(hmul2(hfma2(d, ih, hmul2(d, il)), c1), sh);
}

#define R8(a, i) "+f"(a[i]), "+f"(a[i + 1]), "+f"(a[i + 2]), "+f"(a[i + 3]), "+f"(a[i + 4]), "+f"(a[i + 5]), "+f"(a[i + 6]), "+f"(a[i + 7])
#define D64 "{%0,%1,%2,%3,%4,%5,%6,%7,%8,%9,%10,%11,%12,%13,%14,%15,%16,%17,%18,%19,%20,%21,%22,%23,%24,%25,%26,%27,%28,%29,%30,%31," \
            "%32,%33,%34,%35,%36,%37,%38,%39,%40,%41,%42,%43,%44,%45,%46,%47,%48,%49,%50,%51,%52,%53,%54,%55,%56,%57,%58,%59,%60,%61,%62,%63}"
template <int TB>
__device__ __forceinline__ void mma_ss(float (&d)[64], uint64_t da, uint64_t db, int sc) {
  asm volatile("{\n.reg .pred p;\nsetp.ne.b32 p, %66, 0;\n"
               "wgmma.mma_async.sync.aligned.m64n128k16.f32.bf16.bf16 " D64 ", %64, %65, p, 1, 1, 0, %67;\n}"
               : R8(d, 0), R8(d, 8), R8(d, 16), R8(d, 24), R8(d, 32), R8(d, 40), R8(d, 48), R8(d, 56)
               : "l"(da), "l"(db), "r"(sc), "n"(TB));
}
template <int TB>
__device__ __forceinline__ void mma_rs(float (&d)[64], uint32_t a0, uint32_t a1, uint32_t a2, uint32_t a3, uint64_t db, int sc) {
  asm volatile("{\n.reg .pred p;\nsetp.ne.b32 p, %69, 0;\n"
               "wgmma.mma_async.sync.aligned.m64n128k16.f32.bf16.bf16 " D64 ", {%64,%65,%66,%67}, %68, p, 1, 1, %70;\n}"
               : R8(d, 0), R8(d, 8), R8(d, 16), R8(d, 24), R8(d, 32), R8(d, 40), R8(d, 48), R8(d, 56)
               : "r"(a0), "r"(a1), "r"(a2), "r"(a3), "l"(db), "r"(sc), "n"(TB));
}
#define D128 "{%0,%1,%2,%3,%4,%5,%6,%7,%8,%9,%10,%11,%12,%13,%14,%15,%16,%17,%18,%19,%20,%21,%22,%23,%24,%25,%26,%27,%28,%29,%30,%31," \
             "%32,%33,%34,%35,%36,%37,%38,%39,%40,%41,%42,%43,%44,%45,%46,%47,%48,%49,%50,%51,%52,%53,%54,%55,%56,%57,%58,%59,%60,%61,%62,%63," \
             "%64,%65,%66,%67,%68,%69,%70,%71,%72,%73,%74,%75,%76,%77,%78,%79,%80,%81,%82,%83,%84,%85,%86,%87,%88,%89,%90,%91,%92,%93,%94,%95," \
             "%96,%97,%98,%99,%100,%101,%102,%103,%104,%105,%106,%107,%108,%109,%110,%111,%112,%113,%114,%115,%116,%117,%118,%119,%120,%121,%122,%123,%124,%125,%126,%127}"
#define R128(d, e) R8(d, 0), R8(d, 8), R8(d, 16), R8(d, 24), R8(d, 32), R8(d, 40), R8(d, 48), R8(d, 56), \
                   R8(e, 0), R8(e, 8), R8(e, 16), R8(e, 24), R8(e, 32), R8(e, 40), R8(e, 48), R8(e, 56)
__device__ __forceinline__ void mma256_ss(float (&d)[64], float (&e)[64], uint64_t da, uint64_t db, int sc) {
  asm volatile("{\n.reg .pred p;\nsetp.ne.b32 p, %130, 0;\n"
               "wgmma.mma_async.sync.aligned.m64n256k16.f32.bf16.bf16 " D128 ", %128, %129, p, 1, 1, 0, 1;\n}"
               : R128(d, e) : "l"(da), "l"(db), "r"(sc));
}
__device__ __forceinline__ void mma256_rs(float (&d)[64], float (&e)[64], uint32_t a0, uint32_t a1, uint32_t a2, uint32_t a3, uint64_t db) {
  asm volatile("{\n.reg .pred p;\nsetp.ne.b32 p, 1, 0;\n"
               "wgmma.mma_async.sync.aligned.m64n256k16.f32.bf16.bf16 " D128 ", {%128,%129,%130,%131}, %132, p, 1, 1, 1;\n}"
               : R128(d, e) : "r"(a0), "r"(a1), "r"(a2), "r"(a3), "l"(db));
}
template <int N> __device__ __forceinline__ void keep(float (&a)[N]) {
#pragma unroll
  for (int i = 0; i < N; i++) asm volatile("" : "+f"(a[i])::"memory");
}
template <int N> __device__ __forceinline__ void keep(uint32_t (&a)[N]) {
#pragma unroll
  for (int i = 0; i < N; i++) asm volatile("" : "+r"(a[i])::"memory");
}

#define PROF(cond, idx) do {} while (0)

constexpr float SCL2 = 1.4426950408889634f * 0.08838834764831845f;

__device__ __forceinline__ void pack_p(const float (&s)[64], uint32_t (&p)[32]) {
#pragma unroll
  for (int i = 0; i < 32; i++) p[i] = pack_bf(s[2 * i], s[2 * i + 1]);
}

__device__ __forceinline__ void issue_qk(float (&s)[64], uint32_t q0, uint32_t q1, uint32_t kslot) {
  const uint64_t db = make_desc(kslot, 16, 1024), da0 = make_desc(q0, 16, 1024), da1 = make_desc(q1, 16, 1024);
#pragma unroll
  for (int kk = 0; kk < 8; kk++) mma_ss<0>(s, (kk < 4 ? da0 : da1) + (kk & 3) * 2, db + (kk >> 2) * 1024 + (kk & 3) * 2, kk != 0);
}
__device__ __forceinline__ void issue_pv(float (&o)[64], uint32_t (&p)[32], uint32_t vslot, int acc) {
  uint64_t db = make_desc(vslot, 16384, 1024);
#pragma unroll
  for (int kk = 0; kk < 8; kk++)
    mma_rs<1>(o, p[4 * kk], p[4 * kk + 1], p[4 * kk + 2], p[4 * kk + 3], db + kk * 128, kk == 0 ? acc : 1);
}

template <int H>
__device__ __forceinline__ void store_chunk(const float (&a)[64], uint32_t addr) {
#pragma unroll
  for (int i = 8 * H; i < 8 * H + 8; i += 2)
    stmatrix4(addr ^ ((i & 7) << 4), pack_bf(a[4 * i], a[4 * i + 1]), pack_bf(a[4 * i + 2], a[4 * i + 3]),
              pack_bf(a[4 * i + 4], a[4 * i + 5]), pack_bf(a[4 * i + 6], a[4 * i + 7]));
}
template <int H>
__device__ __forceinline__ void store_chunk(const float (&a)[64], float i0, float i1, uint32_t addr) {
#pragma unroll
  for (int i = 8 * H; i < 8 * H + 8; i += 2)
    stmatrix4(addr ^ ((i & 7) << 4), pack_bf(a[4 * i] * i0, a[4 * i + 1] * i0), pack_bf(a[4 * i + 2] * i1, a[4 * i + 3] * i1),
              pack_bf(a[4 * i + 4] * i0, a[4 * i + 5] * i0), pack_bf(a[4 * i + 6] * i1, a[4 * i + 7] * i1));
}
__device__ __forceinline__ float inv_quad_sum(float l) {
  l += __shfl_xor_sync(0xffffffffu, l, 1);
  l += __shfl_xor_sync(0xffffffffu, l, 2);
  return __fdividef(1.f, l);
}

__device__ __forceinline__ void ln_scalars(float mean, float var, float& mb, float& sd) {
  mb = rbf(mean);
  sd = rbf(sqrtf(rbf(rbf(var) + 1e-5f)));
}

__global__ void __cluster_dims__(2, 1, 1) __launch_bounds__(384, 1) fused_kernel(const __grid_constant__ Maps maps, const Ptrs P) {
  extern __shared__ __align__(1024) uint8_t smem_raw[];
  const uint32_t base = smem_u32(smem_raw);
  const int tid = threadIdx.x, lane = tid & 31;
  const int warp = __shfl_sync(0xffffffffu, tid >> 5, 0);
  const int b = blockIdx.x;
  PROF(tid == 0, 0);

  if (b >= NMAIN) {
    float* sc = reinterpret_cast<float*>(smem_raw);
    float* red = sc + DM;
    for (int k = tid; k < DM; k += 384) sc[k] = rbf(silu_f(__bfloat162float(P.c[k])));
    __syncthreads();
    if (tid < 256) {
      const int col = 2048 + (b - NMAIN) * 1024 + (tid & 127) * 8, r0 = (tid >> 7) * 512;
      float acc[8];
#pragma unroll
      for (int e = 0; e < 8; e++) acc[e] = 0.f;
      for (int r = r0; r < r0 + 512; r += 32) {
        uint4 w[32];
#pragma unroll
        for (int u = 0; u < 32; u++) w[u] = ldg_nc4(P.w_mod + (size_t)(r + u) * NMOD + col);
#pragma unroll
        for (int u = 0; u < 32; u++) {
          float s = sc[r + u];
          acc[0] += s * bf_lo(w[u].x); acc[1] += s * bf_hi(w[u].x); acc[2] += s * bf_lo(w[u].y); acc[3] += s * bf_hi(w[u].y);
          acc[4] += s * bf_lo(w[u].z); acc[5] += s * bf_hi(w[u].z); acc[6] += s * bf_lo(w[u].w); acc[7] += s * bf_hi(w[u].w);
        }
      }
      if (tid >= 128) {
#pragma unroll
        for (int e = 0; e < 8; e++) red[(tid & 127) * 8 + e] = acc[e];
      }
      const uint32_t tag = ld_relaxed(&g_epoch) % 3 + 1;
      bar_sync(1, 256);
      if (tid < 128) {
        uint32_t o[8];
#pragma unroll
        for (int e = 0; e < 8; e++) o[e] = __float_as_uint(rbf(acc[e] + red[tid * 8 + e])) | tag;
        st_relaxed4(g_mod + col, o[0], o[1], o[2], o[3]);
        st_relaxed4(g_mod + col + 4, o[4], o[5], o[6], o[7]);
      }
    }
    PROF(tid == 0, 1);
    return;
  }

  const int rank = b & 1;
  const int rb = ((b >> 4) << 1) | rank, cj = (b >> 1) & 7;
  const uint32_t bfull = base + OFF_BAR, bempty = bfull + NSLOT * 8;
  const uint32_t gfull = bempty + NSLOT * 8, gempty = gfull + 32;
  const uint32_t bar_ofull = gempty + 32;
  const uint32_t bar_ofree = bar_ofull + 16;
  const uint32_t bar_par = bar_ofree + 32;
  const uint32_t bar_mod = bar_par + 8;
  const uint32_t bar_pread = bar_mod + 8;
  const uint32_t bar_xres = bar_pread + 8;
  const uint32_t bar_w1 = bar_xres + 8;
  const uint32_t bar_w2 = bar_w1 + 8;
  const uint32_t bar_last = bar_w2 + 8;
  const uint32_t bar_ring = bar_last + 16;
  const uint32_t bar_box = bar_ring + 8;
  const uint32_t bar_go = bar_box + 96;
  const uint32_t bar_go2 = bar_go + 16;
  const uint32_t bar_cnt = bar_go + 24;
  const uint32_t xfull = bar_go + 32, xempty = xfull + 32;
  const uint32_t bar_hw = xempty + 32, bar_hx = bar_hw + 8;
  const uint32_t bar_hpub = bar_hx + 16;
  const uint32_t bar_ring0 = bar_hpub + 8;
  const uint32_t bar_res = bar_ring0 + 8;
  const uint32_t bar_rst = bar_go + 8;
  const uint32_t stage = base + OFF_STAGE, par = base + OFF_PAR;

  if (tid == 256) {
    for (int s = 0; s < NSLOT; s++) { mbar_init(bfull + s * 8, 1); mbar_init(bempty + s * 8, 16); }
    for (int s = 0; s < 4; s++) { mbar_init(gfull + s * 8, 1); mbar_init(gempty + s * 8, 16); mbar_init(xfull + s * 8, 1); mbar_init(xempty + s * 8, 8); mbar_init(bar_ofree + s * 8, 1); }
    mbar_init(bar_ofull, 128); mbar_init(bar_ofull + 8, 128);
    mbar_init(bar_par, 64); mbar_init(bar_mod, 256); mbar_init(bar_pread, 8); mbar_init(bar_xres, 1);
    mbar_init(bar_w1, 1); mbar_init(bar_w2, 1); mbar_init(bar_last, 1); mbar_init(bar_last + 8, 1); mbar_init(bar_ring, 8); mbar_init(bar_go, 1); mbar_init(bar_go2, 1); mbar_init(bar_cnt, 1); mbar_init(bar_rst, 64); mbar_init(bar_hpub, 8); mbar_init(bar_ring0, 8); mbar_init(bar_res, 1);
    for (int s = 0; s < 12; s++) mbar_init(bar_box + s * 8, 1);
    asm volatile("fence.mbarrier_init.release.cluster;" ::: "memory");
    prefetch_map(&maps.x); prefetch_map(&maps.wq); prefetch_map(&maps.k); prefetch_map(&maps.v);
  }
  if (tid == 288) {
    mbar_init(bar_hw, 1); mbar_init(bar_hx, 1); mbar_init(bar_hx + 8, 1);
    asm volatile("fence.mbarrier_init.release.cluster;" ::: "memory");
    mbar_expect_tx(bar_hw, 32768);
    mbar_expect_tx(bar_hx, 16384);
    mbar_expect_tx(bar_hx + 8, 16384);
    const __nv_bfloat16* xs = P.x + (size_t)(rb * 128 + cj * 16) * DM;
    bulk_load(base + 2 * GST_BYTES, xs, 16384, bar_hx);
    tma2d(stage, &maps.wm, (b >> 1) * 32, rank * 512, bar_hw);
    tma2d(stage + 16384, &maps.wm, (b >> 1) * 32, rank * 512 + 256, bar_hw);
    bulk_load(base + 3 * GST_BYTES, xs + 8 * DM, 16384, bar_hx + 8);
  }
  cluster_arrive();

  if (warp >= 8) {
    asm volatile("setmaxnreg.dec.sync.aligned.u32 40;");
    if (warp < 10) bar_arrive(1, 320);
    cluster_wait();
    if (warp == 8) {
      if (lane == 0) {
        uint32_t gph = 1;
        const int kvrow = (cj >> 1) * SK + (SK - WIN);
        int wch = cj * 8 + rank * 2;
#pragma unroll 1
        for (int ps = 0; ps < 3; ps++) {
          const CUtensorMap* mw = ps == 2 ? &maps.wo : &maps.wq;
                    const uint32_t xt = ps == 1 ? XT1 : XT2, wt = ps == 0 ? WT0 : (ps == 1 ? WT1 : WT2);
          const int nst = ps == 2 ? 32 : 16;
          if (ps) {
            const uint32_t epoch = ld_relaxed(&g_epoch);
            wait_counter(ps == 1 ? &g_cnt_h[rb * 32] : &g_cnt_o[(rb * 8 + (cj & 1)) * 32], 8 * (epoch + 1));
            if (ps == 2) wait_counter(&g_cnt_o[(rb * 8 + 2 + (cj & 1)) * 32], 8 * (epoch + 1));
            fence_async();
            mbar_wait(bar_ofree + (ps - 1) * 16, 0);
          }
#pragma unroll 1
          for (int i = 0; i < nst; i++) {
            if (i == GOST) mbar_arrive(bar_go);
            if (i == RES0 || i == RES1) mbar_arrive(bar_res);
            if (ps == 0 && i == HD) mbar_wait(bar_mod, 0);
            if (ps && i && i < 4) mbar_wait(bempty + (i == 3 ? 3 : i - 1) * 8, 1);
            const uint32_t bf = i < 30 ? gfull + (i & 3) * 8 : bar_last + (i & 1) * 8;
            mbar_wait(gempty + (i & 3) * 8, gph);
            mbar_expect_tx(bf, ps ? GST_BYTES : 2 * UNIT);
            const int kt = ps == 2 ? (((cj & 1) * 4 + ((i >> 1) & 3)) * 4 + (i >> 3)) * 2 + (i & 1) : (i + (ps ? 0 : b & 14)) & 15;
            tma3d_mc<true>(base + unit_of(wt, i & 3) + rank * UNIT, mw, 0, kt * 64, wch, bf);
            if (i == 16) mbar_wait(bar_cnt, 0);
            if (ps && i == 2) mbar_wait(bempty + 16, 1);
            if (ps) bulk_load_stream(base + unit_of(xt, i & 3), g_act + (uint32_t)(rb * 80 + (ps - 1) * 16 + kt) * UNIT, UNIT, bf);
            if ((i & 3) == 3) gph ^= 1;
          }
          if (ps == 2) break;
          if (ps == 1) mbar_arrive(bar_go2);
          wch = ps ? ((wch >> 3) ^ rank) * 2 : wch + 4;
#pragma unroll 1
          for (int u = 0; u < 16; u++) {
            const bool isk = (u == 0) || ((u & 1) && u < 15);
            const int blk = (isk ? (u + 1) >> 1 : (u == 15 ? 7 : (u >> 1) - 1)) & 3;
            const uint32_t sl = base + unit_of(ps ? AT1 : AT0, u & 3), bf = bfull + (u & 3) * 8;
            if (u < 4) mbar_wait(gempty + ((u + 1) >> 1) * 8, gph);
            mbar_wait(bempty + (u & 3) * 8, ((u >> 2) & 1) ^ 1);
            mbar_expect_tx(bf, SLOT_BYTES);
            tma3d_mc<false>(sl + rank * 16384, isk ? &maps.k : &maps.v, 0, kvrow + blk * 128, rank, bf);
          }
        }
        if (b < NFFN) {
          mbar_wait(bar_ring0, 0);
#pragma unroll 1
          for (int u = 0; u < 12 + FPACE; u++) {
            if (u == E0) mbar_wait(bar_ring, 0);
            if (u >= FPACE) {
              mbar_wait(bar_box + (u - FPACE) * 8, 0);
              if (u - FPACE == 7) { mbar_arrive(bar_w1); PROF(true, 59); }
              if (u - FPACE == 11) { mbar_arrive(bar_w2); PROF(true, 60); }
            }
            if (u < 12) {
              mbar_expect_tx(bar_box + u * 8, UNIT);
              if (u < 8) tma2d(base + OFF_GATE + u * UNIT, u < 4 ? &maps.wg : &maps.wu, b * 32, (u & 3) * 256, bar_box + u * 8);
              else tma3d(base + (u - 8) * UNIT, &maps.wd, 0, b * 32, (u - 8) * 4, bar_box + u * 8);
            }
          }
        }
      }
    } else if (warp == 9) {
      if (lane == 0) {
        const uint32_t epoch = ld_relaxed(&g_epoch);
#pragma unroll 1
        for (int i = 0; i < 16; i++) {
          if (i == HDX) mbar_wait(bar_mod, 0);
          if (i == NRS) {
            wait_counter(&g_cnt_h[rb * 32], 8 * (epoch + 1));
            PROF(true, 26);
            fence_async();
            PROF(true, 15);
          }
          mbar_wait(xempty + (i & 3) * 8, ((i >> 2) & 1) ^ 1);
          mbar_expect_tx(xfull + (i & 3) * 8, UNIT);
          if (i < NRS) tma2d(base + (i & 3) * GST_BYTES, &maps.x, ((2 * cj + i) & 15) * 64, rb * 128, xfull + (i & 3) * 8);
          else bulk_load_stream(base + (i & 3) * GST_BYTES, g_act + (uint32_t)(rb * 80 + ((2 * cj + i) & 15)) * UNIT, UNIT, xfull + (i & 3) * 8);
        }
        prefetch_map(&maps.wo);
#pragma unroll 1
        for (int t = 0; t < 4; t++) {
#pragma unroll 1
          for (int w = 0; w < 2; w++) {
            mbar_wait(bar_ofull + w * 8, t & 1);
            uint8_t* dst = g_act + (uint32_t)(rb * 80 + 16 + (cj * 4 + t) * 2) * UNIT + w * 8192;
            bulk_store(dst, base + unit_of(QT, 2 * t) + w * 8192, 8192);
            bulk_store(dst + UNIT, base + unit_of(QT, 2 * t + 1) + w * 8192, 8192);
            asm volatile("cp.async.bulk.commit_group;" ::: "memory");
          }
          asm volatile("cp.async.bulk.wait_group.read 0;" ::: "memory");
          mbar_arrive(bar_ofree + t * 8);
          asm volatile("cp.async.bulk.wait_group 0;" ::: "memory");
          fence_async();
          red_release(&g_cnt_o[((rb * 4 + t) * 2 + (cj >> 2)) * 32], 2);
          if (t == PF2T) for (int u = 0; u < PF2; u++)
            tma3d_prefetch(&maps.wo, 0, ((((cj & 1) * 4 + (b >> 5)) * 4 + u) * 2 + ((b >> 4) & 1)) * 64, (cj ^ rank) * 2);
        }
        wait_counter(&g_cnt_o[(rb * 8 + 4 + (cj & 1)) * 32], 8 * (epoch + 1));
        wait_counter(&g_cnt_o[(rb * 8 + 6 + (cj & 1)) * 32], 8 * (epoch + 1));
        fence_async();
        mbar_arrive(bar_cnt);
        PROF(true, 27);
        mbar_expect_tx(bar_xres, 32768);
        mbar_wait(bar_res, 0);
        tma2d(base + OFF_RES, &maps.x, cj * 128, rb * 128, bar_xres);
        mbar_wait(bar_res, 1);
        tma2d(base + OFF_RES + UNIT, &maps.x, cj * 128 + 64, rb * 128, bar_xres);
      }
      __syncwarp();
      mbar_wait(bar_last, 0);
      bar_arrive(8, 160); bar_arrive(9, 160);
      mbar_wait(bar_last + 8, 0);
      bar_arrive(10, 160); bar_arrive(11, 160);
    } else {
      const int t2 = tid - 320;
      if (t2 == 0) {
        mbar_wait(bar_hpub, 0);
        PROF(true, 24);
        red_release(&g_cnt_h[rb * 32], 1);
        PROF(true, 25);
        prefetch_map(&maps.wg); prefetch_map(&maps.wu); prefetch_map(&maps.wd);
      }
      __syncwarp();
      if (b < NFFN) {
        mbar_wait(bar_go2, 0);
        const __nv_bfloat16* pg = ((b & 1) ? P.w_up : P.w_gate) + (b >> 1) * 64 + (size_t)t2 * FF;
        const __nv_bfloat16* pd = P.w_down + (size_t)b * 32768 + t2 * 64;
        PROF(t2 == 0, 13);
#pragma unroll 1
        for (int i = 0; i < WN; i += WB) {
          uint32_t v[WB];
#pragma unroll
          for (int u = 0; u < WB; u++)
            asm volatile("ld.global.cg.L2::128B.u32 %0, [%1];" : "=r"(v[u]) : "l"(i < 16 ? pg + (size_t)(i + u) * 64 * FF : pd + (i + u - 16) * 4096));
#pragma unroll
          for (int u = 1; u < WB; u++) v[0] ^= v[u];
          sts1(par + PAR_SINK + t2 * 4, v[0]);
        }
        PROF(t2 == 0, 14);
      }
      const uint32_t epoch = ld_relaxed(&g_epoch), tag = epoch % 3 + 1;
      mbar_wait(bar_xres, 0);
      float s1 = 0.f, s2 = 0.f;
#pragma unroll 1
      for (int q = 0; q < 4; q++) {
        const int col = q * 256 + t2 * 4;
        uint4 vsb = poll4(g_mod + 3 * DM + col, tag), vcb = poll4(g_mod + 4 * DM + col, tag);
        uint2 wr = *reinterpret_cast<const uint2*>(P.w_r + col);
        float c0 = rbf(1.f + bf_hi(vcb.x)), c1 = rbf(1.f + bf_hi(vcb.y)), c2 = rbf(1.f + bf_hi(vcb.z)), c3 = rbf(1.f + bf_hi(vcb.w));
        float a0 = c0 * bf_lo(wr.x), a1 = c1 * bf_hi(wr.x), a2 = c2 * bf_lo(wr.y), a3 = c3 * bf_hi(wr.y);
        s1 += (a0 + a1) + (a2 + a3);
        s2 += bf_hi(vsb.x) * bf_lo(wr.x) + bf_hi(vsb.y) * bf_hi(wr.x) + bf_hi(vsb.z) * bf_lo(wr.y) + bf_hi(vsb.w) * bf_hi(wr.y);
        if ((col >> 7) == cj) {
          const int lc = col & 127;
          uint4 vga = poll4(g_mod + 2 * DM + col, tag), vgb = poll4(g_mod + 5 * DM + col, tag);
          sts2(par + PAR_GA + lc * 2, __byte_perm(vga.x, vga.y, 0x7632), __byte_perm(vga.z, vga.w, 0x7632));
          sts2(par + PAR_GB + lc * 2, __byte_perm(vgb.x, vgb.y, 0x7632), __byte_perm(vgb.z, vgb.w, 0x7632));
          sts2(par + PAR_SB + lc * 2, __byte_perm(vsb.x, vsb.y, 0x7632), __byte_perm(vsb.z, vsb.w, 0x7632));
          sts2(par + PAR_CB1 + lc * 2, pack_bf(c0, c1), pack_bf(c2, c3));
          sts4(par + PAR_A + lc * 4, make_uint4(__float_as_uint(a0), __float_as_uint(a1), __float_as_uint(a2), __float_as_uint(a3)));
        }
      }
#pragma unroll
      for (int o = 16; o > 0; o >>= 1) { s1 += __shfl_xor_sync(0xffffffffu, s1, o); s2 += __shfl_xor_sync(0xffffffffu, s2, o); }
      if (lane == 0) { sts2(par + PAR_CONST + (warp - 10) * 8, __float_as_uint(s1), __float_as_uint(s2)); sts1(par + PAR_CONST + 48, epoch); }
      if (t2 < 2) {
        uint4 g = poll4(g_mod + 5 * DM + b * 8 + t2 * 4, tag);
        sts4(par + PAR_CONST + 16 + t2 * 16, g);
      }
      mbar_wait(bar_go, 0);
      for (int q = XR; q < XE; q++) st_b128(g_xch + ((size_t)b * 8 * 256 + q * 64 + t2) * 4, (epoch & 1) << 16, 0, 0, 0);
      for (int q = 0; q < 2; q++) st_relaxed4(g_stats + ((size_t)cj * SEQ + rb * 128 + q * 64 + t2) * 4, 0, 0, 0, 0);
      __threadfence();
      mbar_arrive(bar_par);
      mbar_wait(bar_ring, 0);
      if (b < NFFN)
        for (int q = 0; q < 4; q++) st_relaxed4(g_ypart + ((size_t)(q * 32 + (t2 >> 1)) * NFFN + b) * 8 + (t2 & 1) * 4, 0, 0, 0, 0);
      st_relaxed4(g_row + rb * 2 * DM + (t2 >> 5) * DM + cj * 128 + (t2 & 31) * 4, 0, 0, 0, 0);
      if (cj == 0 && t2 < 2) st_relaxed4(g_cand + rb * 8 + t2 * 4, 0, 0, 0, 0);
      __threadfence();
      mbar_arrive(bar_rst);
    }
    __syncwarp();
    cluster_arrive();
    cluster_wait();
  } else {
    const int wg = warp >> 2;

    uint32_t tag;
    {
      uint32_t* const pmod = g_modp + rank * 2 * DM + (b >> 1) * 32 + lane;
      uint32_t* const pln = g_ln1 + (rb * 128 + cj * 16 + warp) * 4;
      const uint32_t cv = ldg_nc1(P.c + rank * 512 + tid * 2);
      const uint32_t epoch = ld_relaxed(&g_epoch);
      if (warp == 0) st_relaxed(pmod, 0);
      if (lane == 0) { st_relaxed2(pln, 0, 0); st_relaxed2(pln + 32, 0, 0); }
      asm volatile("setmaxnreg.inc.sync.aligned.u32 232;");
      sts1(par + tid * 4, pack_bf(silu_f(bf_lo(cv)), silu_f(bf_hi(cv))));
      bar_sync(1, 320);
      tag = epoch % 3 + 1;
#pragma unroll
      for (int part = 0; part < 3; part++) {
        if (part != 1) {
          const uint32_t xa = base + (2 + part / 2) * GST_BYTES + warp * 2048 + lane * 16;
          mbar_wait(bar_hx + part * 4, 0);
          float s0 = 0.f, s1 = 0.f, q0 = 0.f, q1 = 0.f;
#pragma unroll
          for (int q = 0; q < 4; q++) {
            const uint4 xv = lds4(xa + q * 512);
            const uint32_t u[4] = {xv.x, xv.y, xv.z, xv.w};
#pragma unroll
            for (int e = 0; e < 4; e++) { const float lo = bf_lo(u[e]), hi = bf_hi(u[e]); s0 += lo; s1 += hi; q0 += lo * lo; q1 += hi * hi; }
          }
          s0 += s1; q0 += q1;
#pragma unroll
          for (int o = 16; o > 0; o >>= 1) { s0 += __shfl_xor_sync(0xffffffffu, s0, o); q0 += __shfl_xor_sync(0xffffffffu, q0, o); }
          const float mean = s0 * (1.f / DM);
          float mb, sd;
          ln_scalars(mean, fmaxf(q0 * (1.f / DM) - mean * mean, 0.f), mb, sd);
          if (lane == 0) st_relaxed2(pln + part * 16, __float_as_uint(mb) | tag, __float_as_uint(sd) | tag);
          PROF(tid == 0 && part == 2, 4);
        } else {
          float acc[8];
#pragma unroll
          for (int e = 0; e < 8; e++) acc[e] = 0.f;
          const uint32_t wa = stage + (tid >> 2) * 64 + (((tid ^ (tid >> 3)) & 3) << 4), sa = par + (tid >> 3) * 4, sh = (tid & 4) ? 0x3244 : 0x1044;
          mbar_wait(bar_hw, 0);
#pragma unroll
          for (int p = 0; p < 8; p++) {
            const uint4 w = lds4(wa + p * 4096);
            const float s = __uint_as_float(__byte_perm(lds1(sa + p * 128), 0, sh));
            acc[0] += s * bf_lo(w.x); acc[1] += s * bf_hi(w.x); acc[2] += s * bf_lo(w.y); acc[3] += s * bf_hi(w.y);
            acc[4] += s * bf_lo(w.z); acc[5] += s * bf_hi(w.z); acc[6] += s * bf_lo(w.w); acc[7] += s * bf_hi(w.w);
          }
#pragma unroll
          for (int e = 0; e < 4; e++) {
            const bool up = lane & 16;
            acc[e] = (up ? acc[e + 4] : acc[e]) + __shfl_xor_sync(0xffffffffu, up ? acc[e] : acc[e + 4], 16);
          }
#pragma unroll
          for (int e = 0; e < 2; e++) {
            const bool up = lane & 8;
            acc[e] = (up ? acc[e + 2] : acc[e]) + __shfl_xor_sync(0xffffffffu, up ? acc[e] : acc[e + 2], 8);
          }
          {
            const bool up = lane & 4;
            acc[0] = (up ? acc[1] : acc[0]) + __shfl_xor_sync(0xffffffffu, up ? acc[0] : acc[1], 4);
          }
          sts1(par + 1024 + warp * 128 + ((lane & 3) * 8 + (lane >> 2)) * 4, __float_as_uint(acc[0]));
          bar_sync(1, 256);
          if (warp == 0) {
            float s = 0.f;
#pragma unroll
            for (int w8 = 0; w8 < 8; w8++) s += __uint_as_float(lds1(par + 1024 + w8 * 128 + lane * 4));
            st_relaxed(pmod, (__float_as_uint(s) & ~3u) | tag);
          }
          PROF(tid == 0, 3);
        }
      }
      {
        uint2 s0 = ld_relaxed2(g_ln1 + (rb * 128 + (tid & 127)) * 4);
        uint4 v[4];
#pragma unroll
        for (int q = 0; q < 4; q++) v[q] = ld_relaxed4(g_modp + q * DM + tid * 4);
        {
          uint32_t n = 0;
          while (!(tag_ok(v[0], tag) && tag_ok(v[1], tag) && tag_ok(v[2], tag) && tag_ok(v[3], tag))) {
#pragma unroll
            for (int q = 0; q < 4; q++)
              if (!tag_ok(v[q], tag)) v[q] = ld_relaxed4(g_modp + q * DM + tid * 4);
            if (((s0.x ^ tag) | (s0.y ^ tag)) & 3u) s0 = ld_relaxed2(g_ln1 + (rb * 128 + (tid & 127)) * 4);
            watchdog(n);
          }
        }
        const uint32_t d = stage + (tid >> 2) * 64 + (tid & 1) * 32 + (tid & 2) * 2;
        sts1(d, pack_bf(1.f + rbf(untag_sum(v[1].x, v[3].x)), 1.f + rbf(untag_sum(v[1].y, v[3].y))));
        sts1(d + 16, pack_bf(1.f + rbf(untag_sum(v[1].z, v[3].z)), 1.f + rbf(untag_sum(v[1].w, v[3].w))));
        sts1(d + 8, pack_bf(untag_sum(v[0].x, v[2].x), untag_sum(v[0].y, v[2].y)));
        sts1(d + 24, pack_bf(untag_sum(v[0].z, v[2].z), untag_sum(v[0].w, v[2].w)));
        if (wg == 0) {
          uint32_t n = 0;
          while (((s0.x ^ tag) | (s0.y ^ tag)) & 3u) { s0 = ld_relaxed2(g_ln1 + (rb * 128 + tid) * 4); watchdog(n); }
          uint32_t ih, il;
          split_inv(bf_hi(s0.y), ih, il);
          sts4(stage + 4096 + tid * 16, make_uint4(__byte_perm(s0.x, 0, 0x3232), ih, il, 0));
        }
        mbar_arrive(bar_mod);
      }
      cluster_wait();
      if (wg == 1) bar_arrive(2, 256);
      mbar_wait(bar_mod, 0);
      PROF(tid == 0, 2);
    }

    float f0 = 0.f, f1 = 0.f;
    const uint32_t rempty = lane < 2 ? mapa(bempty, lane & 1) : 0;
    constexpr uint32_t GE = NSLOT * 8 + 32;
    float o[64], s[64];
#pragma unroll 1
    for (int ps = 0; ps < 3; ps++) {
      {
        const uint32_t xt = ps == 1 ? XT1 : XT2, wt = ps == 1 ? WT1 : WT2;
        const int nst = ps == 2 ? 28 : 14;
        if (ps == 0) {
          float ga[64], gb[64];
#pragma unroll
          for (int i = 0; i < 64; i++) { ga[i] = 0.f; gb[i] = 0.f; }
          uint32_t a[2][16];
          const uint32_t l = fresh_lane();
          const uint4 r0 = lds4(stage + 4096 + (warp * 16 + (l >> 2)) * 16), r1 = lds4(stage + 4096 + 128 + (warp * 16 + (l >> 2)) * 16);
          auto transform = [&](int i, uint32_t (&f)[16], uint32_t z) {
            const uint32_t ad = base + (i & 3) * GST_BYTES + wg * 8192 + frag_offset(warp) + z;
            mbar_wait(xfull + (i & 3) * 8, i >> 2);
#pragma unroll
            for (int kk = 0; kk < 4; kk++) ldmatrix4(ad ^ (kk * 32), f[4 * kk], f[4 * kk + 1], f[4 * kk + 2], f[4 * kk + 3]);
#pragma unroll
            for (int kk = 0; kk < 4; kk++) {
              const uint4 m = lds4(stage + (l & 3) * 16 + ((2 * cj + i) & 15) * 256 + kk * 64);
              f[4 * kk] = ln_mod(f[4 * kk], r0.x, r0.y, r0.z, m.x, m.z);
              f[4 * kk + 1] = ln_mod(f[4 * kk + 1], r1.x, r1.y, r1.z, m.x, m.z);
              f[4 * kk + 2] = ln_mod(f[4 * kk + 2], r0.x, r0.y, r0.z, m.y, m.w);
              f[4 * kk + 3] = ln_mod(f[4 * kk + 3], r1.x, r1.y, r1.z, m.y, m.w);
            }
            keep(f);
            mbar_arrive_pred(xempty + (i & 3) * 8, l == 0);
          };
          auto publish = [&](int u, uint32_t (&f)[16]) {
            const uint32_t sc = stage + 8192 + wg * 8192;
#pragma unroll
            for (int kk = 0; kk < 4; kk++) stmatrix4((sc + frag_offset(warp)) ^ (kk * 32), f[4 * kk], f[4 * kk + 1], f[4 * kk + 2], f[4 * kk + 3]);
            __syncwarp();
            const uint32_t src = sc + (warp & 3) * 2048 + l * 16;
            uint8_t* dst = g_act + (uint32_t)(rb * 80 + cj * 2 + u) * UNIT + warp * 2048 + l * 16;
#pragma unroll
            for (int p4 = 0; p4 < 4; p4++) stg4(dst + p4 * 512, lds4(src + p4 * 512));
            __syncwarp();
            if (u == 1) mbar_arrive_pred(bar_hpub, l == 0);
          };
          auto multiply = [&](int i, uint32_t (&f)[16]) {
            mbar_wait(gfull + (i & 3) * 8, i >> 2);
            const uint64_t db = make_desc(base + (i & 3) * GST_BYTES + UNIT, 8192, 1024);
            wg_fence();
#pragma unroll
            for (int kk = 0; kk < 4; kk++) mma256_rs(ga, gb, f[4 * kk], f[4 * kk + 1], f[4 * kk + 2], f[4 * kk + 3], db + kk * 128);
            wg_commit();
          };
          transform(0, a[0], 0); publish(0, a[0]); transform(1, a[1], 0); multiply(0, a[0]); publish(1, a[1]);
#pragma unroll
          for (int i = 1; i < NRS; i++) {
            if (i >= 2) {
              uint32_t z = r0.w;
#pragma unroll
              for (int k = 0; k < 16; k += 2) asm volatile("lop3.b32 %0, %1, %2, %0, 0xA8;" : "+r"(z) : "r"(a[i & 1][k]), "r"(a[i & 1][k + 1]));
              transform(i, a[i & 1], z);
            }
            multiply(i, a[i & 1]);
            wg_wait<1>();
            mbar_arrive_cl(rempty, GE + ((i + 3) & 3) * 8);
          }
          mbar_arrive_pred(bar_pread, l == 0);
#pragma unroll 1
          for (int i = NRS; i < 14; i++) {
            mbar_wait(xfull + (i & 3) * 8, (i >> 2) & 1);
            mbar_wait(gfull + (i & 3) * 8, (i >> 2) & 1);
            const uint32_t xa = base + (i & 3) * GST_BYTES;
            const uint64_t da = make_desc(xa + wg * 8192, 16, 1024), db = make_desc(xa + UNIT, 8192, 1024);
            if (i == 13) bar_sync(2 + wg, 256);
            wg_fence();
#pragma unroll
            for (int kk = 0; kk < 4; kk++) mma256_ss(ga, gb, da + kk * 2, db + kk * 128, 1);
            wg_commit();
            if (i == 13) bar_arrive(3 - wg, 256);
            wg_wait<1>();
            uint32_t z = r0.w;
#pragma unroll
            for (int k = 0; k < 16; k += 2) asm volatile("lop3.b32 %0, %1, %2, %0, 0xA8;" : "+r"(z) : "r"(a[1][k]), "r"(a[1][k + 1]));
            mbar_arrive_cl(rempty, GE + ((i + 3) & 3) * 8 + z);
            mbar_arrive_pred(xempty + ((i + 3) & 3) * 8, l == 0 && i != NRS);
          }
          mbar_wait(xfull + 16, 1);
          mbar_wait(xfull + 24, 1);
          wg_wait<0>();
          keep(ga); keep(gb);
#pragma unroll
          for (int i = 0; i < 64; i++) {
            asm volatile("mov.b32 %0, %1;" : "=f"(s[i]) : "f"(ga[i]));
            asm volatile("mov.b32 %0, %1;" : "=f"(o[i]) : "f"(gb[i]));
          }
        } else {
          float ga[64], gb[64];
#pragma unroll
          for (int i = 0; i < 64; i++) {
            asm volatile("mov.b32 %0, %1;" : "=f"(ga[i]) : "f"(s[i]));
            asm volatile("mov.b32 %0, %1;" : "=f"(gb[i]) : "f"(o[i]));
          }
#pragma unroll 1
          for (int i = 0; i < nst; i++) {
            mbar_wait(gfull + (i & 3) * 8, (i >> 2) & 1);
            const uint64_t da = make_desc(base + unit_of(xt, i & 3) + wg * 8192, 16, 1024), db = make_desc(base + unit_of(wt, i & 3), 8192, 1024);
            if (i == nst - 1) bar_sync(2 + wg, 256);
            wg_fence();
#pragma unroll
            for (int kk = 0; kk < 4; kk++) mma256_ss(ga, gb, da + kk * 2, db + kk * 128, kk ? 1 : i);
            wg_commit();
            if (i == nst - 1) bar_arrive(3 - wg, 256);
            wg_wait<1>();
            mbar_arrive_cl(rempty, GE + ((i + 3) & 3) * 8, i != 0);
            PROF(tid == 0 && (i & 3) == 0, 40 + (ps - 1) * 4 + i / 4);
          }
          wg_wait<0>();
          keep(ga); keep(gb);
#pragma unroll
          for (int i = 0; i < 64; i++) {
            asm volatile("mov.b32 %0, %1;" : "=f"(s[i]) : "f"(ga[i]));
            asm volatile("mov.b32 %0, %1;" : "=f"(o[i]) : "f"(gb[i]));
          }
        }
        mbar_arrive_cl(rempty, GE + (ps == 2 ? 24 : 8));
        if (ps == 2) break;
      }
      const uint32_t qw = base + wg * 8192, qt = QT >> (16 * ps), at = ps ? AT1 : AT0;
      {
        const uint32_t wt = ps ? WT1 : WT0;
        const uint64_t da0 = make_desc(qw + unit_of(qt, 2), 16, 1024), da1 = make_desc(qw + unit_of(qt, 3), 16, 1024);
        const uint64_t db0 = make_desc(base + unit_of(wt, 2), 8192, 1024), db1 = make_desc(base + unit_of(wt, 3), 8192, 1024);
        mbar_wait(gfull + 16, 1);
        mbar_wait(gfull + 24, 1);
        bar_sync(2 + wg, 256);
        wg_fence();
#pragma unroll
        for (int kk = 0; kk < 8; kk++) mma_ss<1>(s, (kk < 4 ? da0 : da1) + (kk & 3) * 2, (kk < 4 ? db0 : db1) + (kk & 3) * 128, 1);
        wg_commit();
        bar_arrive(3 - wg, 256);
        mbar_wait(ps == 0 ? bar_pread : bar_ofree + 8, 0);
        mbar_wait(bfull, 0);
        wg_wait<0>();
        keep(s);
        PROF(tid == 0, 8 + ps * 8);
        store_chunk<0>(s, qw + unit_of(qt, 0) + frag_offset(warp));
        store_chunk<1>(s, qw + unit_of(qt, 1) + frag_offset(warp));
        fence_async_smem();
        bar_sync(2 + wg, 256);
        wg_fence();
        issue_qk(s, qw + unit_of(qt, 0), qw + unit_of(qt, 1), base + unit_of(at, 0));
        wg_commit();
#pragma unroll
        for (int kk = 0; kk < 8; kk++) mma_ss<1>(o, (kk < 4 ? da0 : da1) + (kk & 3) * 2, (kk < 4 ? db0 : db1) + UNIT / 16 + (kk & 3) * 128, 1);
        wg_commit();
        bar_arrive(3 - wg, 256);
        wg_wait<1>();
        keep(s);
        mbar_arrive_cl(rempty, 0);
      }
      PROF(tid == 0 && ps == 1, 61);
      float l0 = 0.25f, l1 = 0.25f;
      auto step = [&](auto odd_c, const int j, uint32_t (&pw)[32], uint32_t (&pr)[32]) {
        constexpr bool ODD = decltype(odd_c)::value;
        const bool first = !ODD && (j & 2) == 0, last = ODD && j == 7;
        const uint32_t ph = (j >> 1) & 1;
        float i0, i1, a0, a1;
        if (first) { i0 = inv_quad_sum(l0); i1 = inv_quad_sum(l1); l0 = 0.f; l1 = 0.f; }
        bool redo = !ODD && (j | ps) == 0, again = false;
        while (true) {
          if (redo) {
            float m0 = fmaxf(s[0], s[1]), m1 = fmaxf(s[2], s[3]);
#pragma unroll
            for (int i = 1; i < 16; i++) { m0 = fmaxf(m0, fmaxf(s[4 * i], s[4 * i + 1])); m1 = fmaxf(m1, fmaxf(s[4 * i + 2], s[4 * i + 3])); }
            m0 = fmaxf(m0, __shfl_xor_sync(0xffffffffu, m0, 1)); m1 = fmaxf(m1, __shfl_xor_sync(0xffffffffu, m1, 1));
            m0 = fmaxf(m0, __shfl_xor_sync(0xffffffffu, m0, 2)); m1 = fmaxf(m1, __shfl_xor_sync(0xffffffffu, m1, 2));
            m0 *= SCL2; m1 *= SCL2;
            if (!first) {
              m0 = fmaxf(m0, f0); m1 = fmaxf(m1, f1);
              const float c0 = ex2(f0 - m0), c1 = ex2(f1 - m1);
              l0 *= c0; l1 *= c1;
              wg_wait<0>();
              keep(o);
#pragma unroll
              for (int i = 0; i < 16; i++) { o[4 * i] *= c0; o[4 * i + 1] *= c0; o[4 * i + 2] *= c1; o[4 * i + 3] *= c1; }
            }
            f0 = m0; f1 = m1;
          }
          float b0 = 0.f, b1 = 0.f;
          a0 = 0.f; a1 = 0.f;
#pragma unroll
          for (int i = 0; i < 16; i++) {
            const float e0 = ex2(fmaf(s[4 * i], SCL2, -f0)), e1 = ex2(fmaf(s[4 * i + 1], SCL2, -f0));
            const float e2 = ex2(fmaf(s[4 * i + 2], SCL2, -f1)), e3 = ex2(fmaf(s[4 * i + 3], SCL2, -f1));
            a0 += e0; b0 += e1; a1 += e2; b1 += e3;
            pw[2 * i] = pack_bf(e0, e1); pw[2 * i + 1] = pack_bf(e2, e3);
            if (i == VREL) {
#pragma unroll
              for (int k = 0; k < 2 * VREL + 2; k++) asm volatile("" : "+r"(pw[k])::"memory");
              mbar_wait(bfull + (ODD ? 24 : 8), ph);
              wg_wait<0>();
              mbar_arrive_cl(rempty, ODD ? 16 : (j ? 0 : GE + 16), !again);
              if (!ODD) mbar_arrive_cl(rempty, GE + 24, !again && j == 0);
#pragma unroll
              for (int k = 4 * VREL + 4; k < 64; k++) asm volatile("" : "+f"(s[k])::"memory");
            }
          }
          a0 += b0; a1 += b1;
          if (redo) break;
          redo = __any_sync(0xffffffffu, !(a0 + a1 < 0x1p70f));
          if (first) {
            uint32_t m0 = __ballot_sync(0xffffffffu, a0 > 0x1p-50f), m1 = __ballot_sync(0xffffffffu, a1 > 0x1p-50f);
            m0 |= m0 >> 1; m1 |= m1 >> 1; m0 |= m0 >> 2; m1 |= m1 >> 2;
            redo = redo || (m0 & m1 & 0x11111111u) != 0x11111111u;
          }
          if (!redo) break;
          again = true;
        }
        l0 += a0; l1 += a1;
        keep(pw);
        keep(o);
        const uint32_t qo = qt >> (j ? 0 : 8);
        if (first) store_chunk<0>(o, i0, i1, qw + unit_of(qo, 0) + frag_offset(warp));
        keep(o);
        bar_sync(2 + wg, 256);
        if (!last) {
          const uint32_t qn = qt >> (j >= 3 ? 8 : 0);
          wg_fence();
          issue_qk(s, qw + unit_of(qn, 0), qw + unit_of(qn, 1), base + unit_of(at, ODD ? 3 : 1));
          wg_commit();
          mbar_wait(bfull + (ODD ? 0 : 16), ODD ? ph ^ 1 : ph);
        }
        if (first) { store_chunk<1>(o, i0, i1, qw + unit_of(qo, 1) + frag_offset(warp)); keep(o); }
        wg_fence();
        issue_pv(o, pw, base + unit_of(at, ODD ? (last ? 3 : 0) : 2), !first);
        wg_commit();
        bar_arrive(3 - wg, 256);
        if (first) { fence_async_smem(); mbar_arrive_pred(bar_ofull + wg * 8, j); PROF(tid == 0 && j, 9 + ps * 8); }
        wg_wait<1>();
        keep(s);
        mbar_arrive_cl(rempty, ODD ? 24 : 8, !last);
        PROF(tid == 0 && ps == 1, 51 + j);
      };
      uint32_t pa[32], pb[32];
#pragma unroll 1
      for (int j = 0; j < 8; j += 2) {
        step(std::false_type{}, j, pa, pb);
        step(std::true_type{}, j + 1, pb, pa);
      }
      {
        const float i0 = inv_quad_sum(l0), i1 = inv_quad_sum(l1);
        wg_wait<0>();
        keep(o);
        mbar_arrive_cl(rempty, 24);
        store_chunk<0>(o, i0, i1, qw + unit_of(qt, 2) + frag_offset(warp));
        store_chunk<1>(o, i0, i1, qw + unit_of(qt, 3) + frag_offset(warp));
        fence_async_smem();
        mbar_arrive(bar_ofull + wg * 8);
      }
      PROF(tid == 0, 10 + ps * 8);
    }

    const int ln = fresh_lane(), g = ln >> 2, tq = ln & 3, ct = warp * 32 + ln;
    const bool lane0 = ln == 0;
    const int lrow0 = warp * 16 + g;
    const int grow0 = rb * 128 + lrow0;
    const uint32_t res = base + OFF_RES, trow = res + wg * 8192 + frag_offset(warp);
    uint32_t xr[32];
    {
      const uint64_t da = make_desc(base + wg * 8192, 16, 1024), db = make_desc(base, 8192, 1024);
      constexpr int U = UNIT / 16;
      constexpr int XU[4] = {6, 9, 12, 13}, WU[4] = {7, 10, 0, 2};
#define HALF_STAGE(acc, st, hf) _Pragma("unroll") for (int kk = 0; kk < 4; kk++) mma_ss<1>(acc, da + XU[st] * U + kk * 2, db + (WU[st] + hf) * U + kk * 128, 1)
      PROF(ct == 0, 19);
      mbar_wait(gfull, 1);
      mbar_wait(gfull + 8, 1);
      wg_fence();
      HALF_STAGE(o, 0, 1);
      HALF_STAGE(o, 1, 1);
      bar_sync(8 + wg, 160);
      HALF_STAGE(o, 2, 1);
      HALF_STAGE(s, 0, 0);
      bar_sync(10 + wg, 160);
      HALF_STAGE(o, 3, 1);
      wg_commit();
      HALF_STAGE(s, 1, 0);
      HALF_STAGE(s, 2, 0);
      wg_commit();
      wg_wait<1>();
      keep(o);
      mbar_arrive_pred(bar_ring0, lane0);
      PROF(ct == 0, 20);
      mbar_wait(bar_par, 0);
      uint32_t* xo = g_xch + ((size_t)b * 8 * 256 + ct) * 4;
      const uint32_t par1 = (~lds1(par + PAR_CONST + 48) & 1) << 16;
      uint32_t w[32];
      pack_p(o, w);
#pragma unroll
      for (int i = 0; i < 8; i++) w[4 * i] = (w[4 * i] & ~0x10000u) | par1;
      keep(w);
#pragma unroll
      for (int i = 0; i < 8; i++) st_b128(xo + i * 1024, w[4 * i], w[4 * i + 1], w[4 * i + 2], w[4 * i + 3]);
      wg_fence();
      HALF_STAGE(s, 3, 0);
      wg_commit();
      PROF(ct == 0, 21);
      const uint32_t* xi = g_xch + ((size_t)(b ^ 2) * 8 * 256 + ct) * 4;
      uint4 v[8];
      v[XF] = ld_b128(xi + XF * 1024);
      wg_wait<0>();
      keep(s);
      cluster_arrive();
      PROF(ct == 0, 23);
      uint32_t n = 0;
      while ((v[XF].x & 0x10000u) != par1) { v[XF] = ld_b128(xi + XF * 1024); watchdog(n); }
      PROF(ct == 0, 22);
      mbar_arrive_pred(bar_ring, lane0);
#pragma unroll
      for (int i = 0; i < 8; i++) if (i != XF) v[i] = ld_b128(xi + i * 1024);
      bool ok;
      do {
        ok = true;
#pragma unroll
        for (int i = 0; i < 8; i++)
          if (i != XF && (v[i].x & 0x10000u) != par1) { v[i] = ld_b128(xi + i * 1024); ok = false; }
        watchdog(n);
      } while (!ok);
#pragma unroll
      for (int i = 0; i < 8; i++) {
        s[8 * i] += bf_lo(v[i].x); s[8 * i + 1] += __uint_as_float(v[i].x & 0xfffe0000u); s[8 * i + 2] += bf_lo(v[i].y); s[8 * i + 3] += bf_hi(v[i].y);
        s[8 * i + 4] += bf_lo(v[i].z); s[8 * i + 5] += bf_hi(v[i].z); s[8 * i + 6] += bf_lo(v[i].w); s[8 * i + 7] += bf_hi(v[i].w);
      }
    }
    PROF(ct == 0, 28);
    mbar_wait(bar_xres, 0);
    float su0 = 0.f, su1 = 0.f, sq0 = 0.f, sq1 = 0.f, dt0 = 0.f, dt1 = 0.f;
#pragma unroll
    for (int i = 0; i < 16; i++) {
      if (!(i & 1)) {
        ldmatrix4((trow ^ ((i & 7) << 4)) + (i >> 3) * 16384, xr[2 * i], xr[2 * i + 1], xr[2 * i + 2], xr[2 * i + 3]);
      }
      const uint32_t ga = lds1(par + PAR_GA + (8 * i + 2 * tq) * 2);
      const uint2 av = lds2(par + PAR_A + (8 * i + 2 * tq) * 4);
      const uint32_t u0 = hadd2(xr[2 * i], hmul2(ga, pack_bf(s[4 * i], s[4 * i + 1])));
      const uint32_t u1 = hadd2(xr[2 * i + 1], hmul2(ga, pack_bf(s[4 * i + 2], s[4 * i + 3])));
      xr[2 * i] = u0; xr[2 * i + 1] = u1;
      const float a = bf_lo(u0), c = bf_hi(u0), d = bf_lo(u1), e = bf_hi(u1);
      su0 += a + c; su1 += d + e;
      sq0 += a * a + c * c; sq1 += d * d + e * e;
      dt0 += a * __uint_as_float(av.x) + c * __uint_as_float(av.y);
      dt1 += d * __uint_as_float(av.x) + e * __uint_as_float(av.y);
    }
#pragma unroll
    for (int o2 = 1; o2 < 4; o2 <<= 1) {
      su0 += __shfl_xor_sync(0xffffffffu, su0, o2); su1 += __shfl_xor_sync(0xffffffffu, su1, o2);
      sq0 += __shfl_xor_sync(0xffffffffu, sq0, o2); sq1 += __shfl_xor_sync(0xffffffffu, sq1, o2);
      dt0 += __shfl_xor_sync(0xffffffffu, dt0, o2); dt1 += __shfl_xor_sync(0xffffffffu, dt1, o2);
    }
    if (tq < 2) st_b128(g_stats + ((size_t)cj * SEQ + grow0 + tq * 8) * 4, __float_as_uint(tq ? su1 : su0), __float_as_uint(tq ? sq1 : sq0), __float_as_uint(tq ? dt1 : dt0), tag);
    PROF(ct == 0, 29);
#pragma unroll
    for (int i = 0; i < 16; i += 2) stmatrix4((trow ^ ((i & 7) << 4)) + (i >> 3) * 16384, xr[2 * i], xr[2 * i + 1], xr[2 * i + 2], xr[2 * i + 3]);
    {
      const uint32_t* sp = g_stats + ((size_t)(2 * tq) * SEQ + grow0) * 4;
      uint4 v0 = ld_b128(sp), v1 = ld_b128(sp + SEQ * 4), v2 = ld_b128(sp + 32), v3 = ld_b128(sp + SEQ * 4 + 32);
      uint32_t n = 0;
      while (v0.w != tag || v1.w != tag || v2.w != tag || v3.w != tag) {
        if (v0.w != tag) v0 = ld_b128(sp);
        if (v1.w != tag) v1 = ld_b128(sp + SEQ * 4);
        if (v2.w != tag) v2 = ld_b128(sp + 32);
        if (v3.w != tag) v3 = ld_b128(sp + SEQ * 4 + 32);
        watchdog(n);
      }
      su0 = __uint_as_float(v0.x) + __uint_as_float(v1.x); sq0 = __uint_as_float(v0.y) + __uint_as_float(v1.y); dt0 = __uint_as_float(v0.z) + __uint_as_float(v1.z);
      su1 = __uint_as_float(v2.x) + __uint_as_float(v3.x); sq1 = __uint_as_float(v2.y) + __uint_as_float(v3.y); dt1 = __uint_as_float(v2.z) + __uint_as_float(v3.z);
    }
#pragma unroll
    for (int o2 = 1; o2 < 4; o2 <<= 1) {
      su0 += __shfl_xor_sync(0xffffffffu, su0, o2); su1 += __shfl_xor_sync(0xffffffffu, su1, o2);
      sq0 += __shfl_xor_sync(0xffffffffu, sq0, o2); sq1 += __shfl_xor_sync(0xffffffffu, sq1, o2);
      dt0 += __shfl_xor_sync(0xffffffffu, dt0, o2); dt1 += __shfl_xor_sync(0xffffffffu, dt1, o2);
    }
    PROF(ct == 0, 30);
    float mb0, sd0, mb1, sd1;
    {
      const float m0 = su0 * (1.f / DM), m1 = su1 * (1.f / DM);
      ln_scalars(m0, fmaxf(sq0 * (1.f / DM) - m0 * m0, 0.f), mb0, sd0);
      ln_scalars(m1, fmaxf(sq1 * (1.f / DM) - m1 * m1, 0.f), mb1, sd1);
    }
    const float inv0 = 1.f / sd0, inv1 = 1.f / sd1;
    uint32_t ih0, il0, ih1, il1;
    split_inv(sd0, ih0, il0);
    split_inv(sd1, ih1, il1);
    const uint4 cst = lds4(par + PAR_CONST);
    const float A1 = __uint_as_float(cst.x) + __uint_as_float(cst.z), A2 = __uint_as_float(cst.y) + __uint_as_float(cst.w);
    const float r0 = (dt0 - mb0 * A1) * inv0 + A2, r1 = (dt1 - mb1 * A1) * inv1 + A2;
    float rbest = r1 > r0 ? r1 : r0;
    int ibest = r1 > r0 ? lrow0 + 8 : lrow0;
#pragma unroll
    for (int o2 = 4; o2 < 32; o2 <<= 1) {
      const float ro = __shfl_xor_sync(0xffffffffu, rbest, o2);
      const int io = __shfl_xor_sync(0xffffffffu, ibest, o2);
      if (ro > rbest || (ro == rbest && io < ibest)) { rbest = ro; ibest = io; }
    }
    if (lane0) sts2(par + PAR_RED + warp * 8, __float_as_uint(rbest), ibest);
    PROF(ct == 0, 38);
    mbar_wait(bar_rst, 0);
    bar_sync(1, 256);
    PROF(ct == 0, 39);
    {
      const uint2 cv = lds2(par + PAR_RED + (ln & 7) * 8);
      rbest = __uint_as_float(cv.x); ibest = cv.y;
#pragma unroll
      for (int o2 = 1; o2 < 8; o2 <<= 1) {
        const float ro = __shfl_xor_sync(0xffffffffu, rbest, o2);
        const int io = __shfl_xor_sync(0xffffffffu, ibest, o2);
        if (ro > rbest || (ro == rbest && io < ibest)) { rbest = ro; ibest = io; }
      }
    }
    if (cj == 0 && ct == 0) st_relaxed2(g_cand + rb * 8, tagf(rbest, tag), ((rb * 128 + ibest) << 2) | tag);
    const uint32_t mm0 = pack_bf(mb0, mb0), mm1 = pack_bf(mb1, mb1);
    if ((ibest >> 4) == warp) {
      const bool hi = ibest & 8;
      const int src = (ibest & 7) * 4, ch = g * 2;
      const uint32_t mm = __shfl_sync(0xffffffffu, hi ? mm1 : mm0, src), ih = __shfl_sync(0xffffffffu, hi ? ih1 : ih0, src), il = __shfl_sync(0xffffffffu, hi ? il1 : il0, src);
      const uint32_t xa = res + (ch >> 3) * 16384 + ibest * 128 + (((ch & 7) ^ (ibest & 7)) << 4) + tq * 4;
      const uint32_t x0 = lds1(xa), x1 = lds1(xa ^ 16);
      const uint32_t pc = par + (8 * ch + 2 * tq) * 2;
      const uint32_t h0 = ln_mod(x0, mm, ih, il, lds1(pc + PAR_CB1), lds1(pc + PAR_SB)), h1 = ln_mod(x1, mm, ih, il, lds1(pc + PAR_CB1 + 16), lds1(pc + PAR_SB + 16));
      uint32_t* dst = g_row + rb * 2 * DM + cj * 128 + ln * 4;
      st_pairs(dst, h0, h1, tag);
      st_pairs(dst + DM, x0, x1, tag);
      __syncwarp();
    }
    uint32_t wf[128];
    const uint32_t frow = (ln & 7) + (ln >> 4) * 8;
    const uint32_t wfa = base + OFF_GATE + warp * 8192 + frow * 64 + ((((ln >> 3) & 1) ^ ((frow >> 1) & 3)) << 4);
#define LOAD_WF(f) ldmatrix4t((wfa ^ (((f) & 1) * 32)) + (((f) >> 1) & 1) * 4 * UNIT + ((f) >> 2) * 1024, wf[4 * (f)], wf[4 * (f) + 1], wf[4 * (f) + 2], wf[4 * (f) + 3])
    const bool early = __all_sync(0xffffffffu, b >= NFFN || mbar_test(bar_w1, 0));
    PROF(ct == 0, 37);
#pragma unroll
    for (int i = 0; i < 16; i += 2) {
      uint32_t ov[4];
      if (early) {
#pragma unroll
        for (int mt = 0; mt < 4; mt++) LOAD_WF(i * 2 + mt);
      }
#pragma unroll
      for (int u = 0; u < 2; u++) {
        const int ii = i + u;
        const uint32_t cb1 = lds1(par + PAR_CB1 + (8 * ii + 2 * tq) * 2), sb = lds1(par + PAR_SB + (8 * ii + 2 * tq) * 2);
        const uint32_t gb = lds1(par + PAR_GB + (8 * ii + 2 * tq) * 2);
        const uint32_t h0 = ln_mod(xr[2 * ii], mm0, ih0, il0, cb1, sb), h1 = ln_mod(xr[2 * ii + 1], mm1, ih1, il1, cb1, sb);
        ov[2 * u] = hadd2(xr[2 * ii], hmul2(gb, h0));
        ov[2 * u + 1] = hadd2(xr[2 * ii + 1], hmul2(gb, h1));
      }
      stmatrix4((trow ^ ((i & 7) << 4)) + (i >> 3) * 16384, ov[0], ov[1], ov[2], ov[3]);
    }
    PROF(ct == 0, 31);
    auto store_tile = [&](int skip) {
      const int wrow0 = wg * 64 + (warp & 3) * 16;
#pragma unroll
      for (int p = 0; p < 8; p++) {
        const int row = 2 * p + (ln >> 4), ch = ln & 15;
        const uint4 v = lds4(res + (ch >> 3) * 16384 + (wrow0 + row) * 128 + (((ch & 7) ^ (row & 7)) << 4));
        if (rb * 128 + wrow0 + row != skip) *reinterpret_cast<uint4*>(P.out + (size_t)(rb * 128 + wrow0 + row) * DM + cj * 128 + ch * 8) = v;
      }
    };
    uint2 cv = ld_relaxed2(g_cand + (ln & 15) * 8);
    if (!early) {
      mbar_wait(bar_w1, 0);
#pragma unroll
      for (int f = 0; f < 32; f++) LOAD_WF(f);
    }
    float rwin; int iwin;
    uint4 hv[8];
    uint32_t wd[64];
    const uint32_t wda = base + warp * 8192 + frow * 128 + ((((ln >> 3) & 1) ^ (ln & 7)) << 4);
#define LOAD_WD(f) ldmatrix4t((wda ^ ((((f) >> 1) & 3) * 32)) + ((f) >> 3) * 4096 + ((f) & 1) * 2048, wd[4 * (f)], wd[4 * (f) + 1], wd[4 * (f) + 2], wd[4 * (f) + 3])
    {
      uint32_t n = 0;
      int cur = -1;
      while (true) {
        const bool valid = !(((cv.x ^ tag) | (cv.y ^ tag)) & 3u);
        const uint32_t bits = cv.x & ~3u;
        const uint32_t key = valid ? ((int)bits < 0 ? ~bits : bits | 0x80000000u) : 0u;
        const uint32_t best = __reduce_max_sync(0xffffffffu, key);
        const int src = (__ffs(__ballot_sync(0xffffffffu, key == best)) - 1) & 15;
        if (best && src != cur) {
          cur = src;
#pragma unroll
          for (int i = 0; i < 8; i++) hv[i] = ld_pairs(g_row + cur * 2 * DM + warp * 128 + i * 16 + tq * 4);
        }
        if (__all_sync(0xffffffffu, valid)) break;
        if (!valid) cv = ld_relaxed2(g_cand + (ln & 15) * 8);
        watchdog(n);
      }
      rwin = __uint_as_float(__shfl_sync(0xffffffffu, cv.x, cur) & ~3u);
      iwin = __shfl_sync(0xffffffffu, cv.y, cur) >> 2;
    }
    PROF(ct == 0, 32);
    const uint32_t* wrow = g_row + (iwin >> 7) * 2 * DM;
    if (b < NFFN) {
      {
        uint32_t n = 0;
        bool ok;
        do {
          ok = true;
#pragma unroll
          for (int i = 0; i < 8; i++)
            if (hv[i].y != tag || hv[i].w != tag) { hv[i] = ld_pairs(wrow + warp * 128 + i * 16 + tq * 4); ok = false; }
          watchdog(n);
        } while (!ok);
      }
      __syncwarp();
      PROF(ct == 0, 33);
      float d[8][4];
#pragma unroll
      for (int i = 0; i < 8; i++) { d[i][0] = 0.f; d[i][1] = 0.f; d[i][2] = 0.f; d[i][3] = 0.f; }
#pragma unroll
      for (int ks = 0; ks < 8; ks++) {
#pragma unroll
        for (int mt = 0; mt < 4; mt++) {
          const int r = ks * 16 + mt * 4;
          mma16816(d[mt + (ks & 1) * 4], wf[r], wf[r + 1], wf[r + 2], wf[r + 3], hv[ks].x, hv[ks].z);
        }
        if (ks == 1) mbar_wait(bar_w2, 0);
        if (ks >= 1) {
#pragma unroll
          for (int f = 4 * ks - 4; f < 16 && f < 4 * ks; f++) LOAD_WD(f);
        }
      }
      const uint32_t red = base + OFF_GATE;
      if (tq == 0) {
        const uint32_t dst = red + warp * 8192 + g * 32;
        sts4(dst, make_uint4(__float_as_uint(d[0][0] + d[4][0]), __float_as_uint(d[0][2] + d[4][2]), __float_as_uint(d[1][0] + d[5][0]), __float_as_uint(d[1][2] + d[5][2])));
        sts4(dst + 16, make_uint4(__float_as_uint(d[2][0] + d[6][0]), __float_as_uint(d[2][2] + d[6][2]), __float_as_uint(d[3][0] + d[7][0]), __float_as_uint(d[3][2] + d[7][2])));
      }
      bar_sync(1, 256);
      uint32_t ab[4];
      {
        float G = 0.f, U = 0.f;
        const uint32_t src = red + (ln & 7) * 32 + (ln >> 3) * 4;
#pragma unroll
        for (int w8 = 0; w8 < 8; w8++) { G += __uint_as_float(lds1(src + w8 * 8192)); U += __uint_as_float(lds1(src + w8 * 8192 + 16)); }
        const float act = rbf(silu_f(rbf(G))) * rbf(U);
        const uint32_t pk = pack_bf(act, __shfl_down_sync(0xffffffffu, act, 1));
#pragma unroll
        for (int i = 0; i < 4; i++) ab[i] = __shfl_sync(0xffffffffu, pk, i * 8 + tq * 2);
      }
      PROF(ct == 0, 34);
#pragma unroll
      for (int mt = 0; mt < 8; mt++) {
        d[mt][0] = 0.f; d[mt][1] = 0.f; d[mt][2] = 0.f; d[mt][3] = 0.f;
        mma16816(d[mt], wd[mt * 8], wd[mt * 8 + 1], wd[mt * 8 + 2], wd[mt * 8 + 3], ab[0], ab[1]);
        mma16816(d[mt], wd[mt * 8 + 4], wd[mt * 8 + 5], wd[mt * 8 + 6], wd[mt * 8 + 7], ab[2], ab[3]);
      }
#pragma unroll
      for (int i = 0; i < 4; i++) {
        const int m4 = (i >> 1) * 4, e = (i & 1) * 2;
        const float y = (tq & 2) ? ((tq & 1) ? d[m4 + 3][e] : d[m4 + 2][e]) : ((tq & 1) ? d[m4 + 1][e] : d[m4][e]);
        st_relaxed(g_ypart + ((size_t)(warp * 16 + (m4 + tq) * 2 + (i & 1)) * NFFN + b) * 8 + g, tagf(y, tag));
      }
      PROF(ct == 0, 35);
    }
    store_tile(iwin);
    {
      uint2 fh = make_uint2(0, 0), fx = make_uint2(0, 0);
      const uint32_t* src = wrow + (b >> 1) * 16 + (ct & 3) * 4 + (b & 1) * 2;
      if (ct < 4) { fh = ld_pair(src); fx = ld_pair(src + DM); }
      float y0 = 0.f, y1 = 0.f, y2 = 0.f, y3 = 0.f;
      if (ct < 2 * NFFN) {
        const uint4 v = poll4(g_ypart + (size_t)b * NFFN * 8 + ct * 4, tag);
        y0 = __uint_as_float(v.x & ~3u); y1 = __uint_as_float(v.y & ~3u); y2 = __uint_as_float(v.z & ~3u); y3 = __uint_as_float(v.w & ~3u);
      }
      __syncwarp();
      PROF(ct == 0, 5); PROF(ct == 96, 11); PROF(ct == 192, 12);
      if (ct < 4) {
        uint32_t n = 0;
        while (fh.y != tag || fx.y != tag) { fh = ld_pair(src); fx = ld_pair(src + DM); watchdog(n); }
      }
#pragma unroll
      for (int o2 = 2; o2 < 32; o2 <<= 1) {
        y0 += __shfl_xor_sync(0xffffffffu, y0, o2); y1 += __shfl_xor_sync(0xffffffffu, y1, o2);
        y2 += __shfl_xor_sync(0xffffffffu, y2, o2); y3 += __shfl_xor_sync(0xffffffffu, y3, o2);
      }
      if (ln < 2) sts4(par + PAR_RED + 64 + warp * 32 + ln * 16, make_uint4(__float_as_uint(y0), __float_as_uint(y1), __float_as_uint(y2), __float_as_uint(y3)));
      PROF(ct == 0, 6);
      bar_sync(1, 256);
      PROF(ct == 0, 7);
      if (ct < 4) {
        float ya = 0.f, yb = 0.f;
#pragma unroll
        for (int w8 = 0; w8 < 7; w8++) {
          const uint2 v = lds2(par + PAR_RED + 64 + w8 * 32 + ct * 8);
          ya += __uint_as_float(v.x); yb += __uint_as_float(v.y);
        }
        const float rs = rbf(1.f / (1.f + __expf(-rbf(rwin))));
        const uint2 gv = lds2(par + PAR_CONST + 16 + ct * 8);
        const uint32_t upd = hmul2(pack_bf(ya, yb), pack_bf(rs, rs));
        *reinterpret_cast<uint32_t*>(P.out + (size_t)iwin * DM + b * 8 + ct * 2) =
            hadd2(fx.x, hmul2(__byte_perm(gv.x, gv.y, 0x7632), hadd2(fh.x, upd)));
      }
      if (b == 0 && ct == 0) st_relaxed(&g_epoch, lds1(par + PAR_CONST + 48) + 1);
    }
    PROF(ct == 0, 36);
    cluster_wait();
  }
}

typedef CUresult (*EncodeFn)(CUtensorMap*, CUtensorMapDataType, cuuint32_t, void*, const cuuint64_t*, const cuuint64_t*,
                             const cuuint32_t*, const cuuint32_t*, CUtensorMapInterleave, CUtensorMapSwizzle,
                             CUtensorMapL2promotion, CUtensorMapFloatOOBfill);

void map2d(EncodeFn enc, CUtensorMap* m, const void* p, uint64_t rows, uint64_t cols, uint32_t brows) {
  cuuint64_t dims[2] = {cols, rows}, strides[1] = {cols * 2};
  cuuint32_t box[2] = {64, brows}, es[2] = {1, 1};
  enc(m, CU_TENSOR_MAP_DATA_TYPE_BFLOAT16, 2, const_cast<void*>(p), dims, strides, box, es, CU_TENSOR_MAP_INTERLEAVE_NONE,
      CU_TENSOR_MAP_SWIZZLE_128B, CU_TENSOR_MAP_L2_PROMOTION_L2_256B, CU_TENSOR_MAP_FLOAT_OOB_FILL_NONE);
}
void map2d_narrow(EncodeFn enc, CUtensorMap* m, const void* p, uint64_t rows, uint64_t cols) {
  cuuint64_t dims[2] = {cols, rows}, strides[1] = {cols * 2};
  cuuint32_t box[2] = {32, 256}, es[2] = {1, 1};
  enc(m, CU_TENSOR_MAP_DATA_TYPE_BFLOAT16, 2, const_cast<void*>(p), dims, strides, box, es, CU_TENSOR_MAP_INTERLEAVE_NONE,
      CU_TENSOR_MAP_SWIZZLE_64B, CU_TENSOR_MAP_L2_PROMOTION_L2_64B, CU_TENSOR_MAP_FLOAT_OOB_FILL_NONE);
}
void map3d(EncodeFn enc, CUtensorMap* m, const void* p, uint64_t rows, uint64_t cols, uint32_t brows, uint32_t nch) {
  cuuint64_t dims[3] = {64, rows, cols / 64}, strides[2] = {cols * 2, 128};
  cuuint32_t box[3] = {64, brows, nch}, es[3] = {1, 1, 1};
  enc(m, CU_TENSOR_MAP_DATA_TYPE_BFLOAT16, 3, const_cast<void*>(p), dims, strides, box, es, CU_TENSOR_MAP_INTERLEAVE_NONE,
      CU_TENSOR_MAP_SWIZZLE_128B, CU_TENSOR_MAP_L2_PROMOTION_L2_256B, CU_TENSOR_MAP_FLOAT_OOB_FILL_NONE);
}

}

extern "C" void kernel_launch(void* const* d_in, const int* in_sizes, int n_in, void* d_out, int out_size) {
  (void)in_sizes; (void)n_in; (void)out_size;
  static EncodeFn enc = nullptr;
  if (!enc) {
    void* fn = nullptr;
    cudaDriverEntryPointQueryResult st;
    cudaGetDriverEntryPoint("cuTensorMapEncodeTiled", &fn, cudaEnableDefault, &st);
    enc = (EncodeFn)fn;
    cudaFuncSetAttribute(fused_kernel, cudaFuncAttributeMaxDynamicSharedMemorySize, SMEM_BYTES);
  }
  Maps maps;
  map2d(enc, &maps.x, d_in[0], SEQ, DM, 128);
  map3d(enc, &maps.wq, d_in[3], DM, NQ, 64, 2);
  map3d(enc, &maps.k, d_in[1], 4 * SK, 128, 128, 1);
  map3d(enc, &maps.v, d_in[2], 4 * SK, 128, 128, 1);
  map3d(enc, &maps.wo, d_in[4], NQ, DM, 64, 2);
  map2d_narrow(enc, &maps.wg, d_in[7], DM, FF);
  map2d_narrow(enc, &maps.wu, d_in[8], DM, FF);
  map3d(enc, &maps.wd, d_in[9], FF, DM, 32, 4);
  map2d_narrow(enc, &maps.wm, d_in[11], DM, NMOD);
  Ptrs p;
  p.x = (const __nv_bfloat16*)d_in[0];
  p.w_r = (const __nv_bfloat16*)d_in[6];
  p.w_gate = (const __nv_bfloat16*)d_in[7];
  p.w_up = (const __nv_bfloat16*)d_in[8];
  p.w_down = (const __nv_bfloat16*)d_in[9];
  p.c = (const __nv_bfloat16*)d_in[10];
  p.w_mod = (const __nv_bfloat16*)d_in[11];
  p.out = (__nv_bfloat16*)d_out;
  fused_kernel<<<NMAIN + NHELP, 384, SMEM_BYTES>>>(maps, p);
}
```

```cpp
#include <cuda_runtime.h>
#include <cuda_bf16.h>
#include <cuda.h>
#include <stdint.h>
#include <type_traits>

#define HD 1
#define HDX 2
#define XF 4
#define XE 32
#define XR 16
#define PF2 1
#define PF2T 1
#define NRS 6
#define FPACE 2
#define GOST 24
#define WB 2
#define WN 16
#define RES0 17
#define RES1 20
#define HU 16
#define VREL 7
#define E0 3

namespace {

constexpr int SEQ = 2048, DM = 1024, NQ = 4096, SK = 2048, WIN = 512, FF = 3584, NMOD = 6144;
constexpr int NMAIN = 128, NHELP = 4, NFFN = 112;
constexpr int NSLOT = 4, SLOT_BYTES = 32768, UNIT = 16384, GST_BYTES = 3 * UNIT;
constexpr uint32_t XT0 = 0x9630, XT1 = 0x54DC, XT2 = 0xDC96;
constexpr uint32_t WT0 = 0xA741, WT1 = 0x720A, WT2 = 0x20A7;
constexpr uint32_t AT0 = 0x7420, AT1 = 0x2C0A;
constexpr uint32_t QT = 0x549696DC;
constexpr int OFF_STAGE = 12 * UNIT;
constexpr int OFF_RES = 4 * UNIT, OFF_GATE = 6 * UNIT;
constexpr int OFF_PAR = 14 * UNIT;
constexpr int OFF_BAR = OFF_PAR + 2048 + 512;
constexpr int SMEM_BYTES = OFF_BAR + 512;
static_assert(SMEM_BYTES <= 232448, "smem");

constexpr int PAR_GA = 0, PAR_CB1 = 256, PAR_SB = 512, PAR_GB = 768;
constexpr int PAR_A = 1024;
constexpr int PAR_CONST = 1536;
constexpr int PAR_RED = 1600;
constexpr int PAR_SINK = 2176;

struct Maps {
  CUtensorMap x, wq, k, v, wo, wg, wu, wd, wm;
};
struct Ptrs {
  const __nv_bfloat16 *x, *w_r, *c, *w_mod, *w_gate, *w_up, *w_down;
  __nv_bfloat16* out;
};

__device__ __align__(1024) uint8_t g_act[16 * 80 * UNIT];
__device__ __align__(128) uint32_t g_mod[NMOD];
__device__ __align__(128) uint32_t g_modp[2 * 2 * DM];
__device__ __align__(128) uint32_t g_ln1[SEQ * 4];
__device__ __align__(128) uint32_t g_cnt_h[16 * 32];
__device__ __align__(128) uint32_t g_cnt_o[128 * 32];
__device__ __align__(128) uint32_t g_xch[NMAIN * 8 * 256 * 4];
__device__ __align__(128) uint32_t g_stats[8 * SEQ * 4];
__device__ __align__(128) uint32_t g_cand[16 * 8];
__device__ __align__(128) uint32_t g_row[16 * 2 * DM];
__device__ __align__(128) uint32_t g_ypart[NMAIN * NFFN * 8];
__device__ uint32_t g_epoch;

__device__ __forceinline__ uint32_t fresh_lane() { uint32_t l; asm volatile("mov.u32 %0, %%laneid;" : "=r"(l)); return l; }
__device__ __forceinline__ uint32_t frag_offset(int warp) {
  const uint32_t l = fresh_lane();
  return ((warp & 3) * 16 + (l & 15)) * 128 + (((l >> 4) ^ (l & 7)) << 4);
}
__device__ __forceinline__ bool elect_one() {
  uint32_t p;
  asm volatile("{ .reg .pred q; elect.sync _|q, 0xffffffff; selp.u32 %0, 1, 0, q; }" : "=r"(p));
  return p;
}
__device__ __forceinline__ uint32_t smem_u32(const void* p) { return (uint32_t)__cvta_generic_to_shared(p); }
__device__ __forceinline__ void mbar_init(uint32_t bar, uint32_t cnt) {
  asm volatile("mbarrier.init.shared::cta.b64 [%0], %1;" ::"r"(bar), "r"(cnt) : "memory");
}
__device__ __forceinline__ void mbar_expect_tx(uint32_t bar, uint32_t bytes) {
  asm volatile("mbarrier.arrive.expect_tx.shared::cta.b64 _, [%0], %1;" ::"r"(bar), "r"(bytes) : "memory");
}
__device__ __forceinline__ void mbar_arrive(uint32_t bar) {
  asm volatile("mbarrier.arrive.shared::cta.b64 _, [%0];" ::"r"(bar) : "memory");
}
__device__ __forceinline__ void mbar_arrive_pred(uint32_t bar, bool p) {
  asm volatile("{ .reg .pred p; setp.ne.b32 p, %1, 0; @p mbarrier.arrive.shared::cta.b64 _, [%0]; }" ::"r"(bar), "r"((int)p) : "memory");
}
__device__ __forceinline__ void mbar_arrive_cl(uint32_t bar, uint32_t off, bool p = true) {
  asm volatile("{ .reg .pred p, q; .reg .b32 a; setp.ne.b32 q, %2, 0; setp.ne.and.b32 p, %0, 0, q; add.u32 a, %0, %1; @p mbarrier.arrive.shared::cluster.b64 _, [a]; }"
               ::"r"(bar), "r"(off), "r"((int)p) : "memory");
}
__device__ __forceinline__ uint32_t mapa(uint32_t addr, uint32_t cta) {
  uint32_t r; asm("mapa.shared::cluster.u32 %0, %1, %2;" : "=r"(r) : "r"(addr), "r"(cta)); return r;
}
__device__ __forceinline__ void cluster_arrive() { asm volatile("barrier.cluster.arrive.relaxed.aligned;" ::: "memory"); }
__device__ __forceinline__ void cluster_wait() { asm volatile("barrier.cluster.wait.aligned;" ::: "memory"); }
__device__ __forceinline__ void watchdog(uint32_t& n) {
}
__device__ __forceinline__ void mbar_wait(uint32_t bar, uint32_t parity) {
  asm volatile("{\n.reg .pred p;\nWAIT_%=:\nmbarrier.try_wait.parity.shared::cta.b64 p, [%0], %1;\n@!p bra WAIT_%=;\n}" ::"r"(bar), "r"(parity) : "memory");
}
__device__ __forceinline__ bool mbar_test(uint32_t bar, uint32_t parity) {
  uint32_t ok;
  asm volatile("{\n.reg .pred p;\nmbarrier.test_wait.parity.shared::cta.b64 p, [%1], %2;\nselp.u32 %0, 1, 0, p;\n}" : "=r"(ok) : "r"(bar), "r"(parity) : "memory");
  return ok;
}
__device__ __forceinline__ uint64_t l2_stream() {
  uint64_t f; asm("createpolicy.fractional.L2::evict_first.b64 %0, 1.0;" : "=l"(f)); return f;
}
__device__ __forceinline__ void tma2d(uint32_t dst, const CUtensorMap* m, int c0, int c1, uint32_t bar) {
  asm volatile("cp.async.bulk.tensor.2d.shared::cluster.global.mbarrier::complete_tx::bytes.L2::cache_hint [%0], [%1, {%3, %4}], [%2], %5;"
               ::"r"(dst), "l"(m), "r"(bar), "r"(c0), "r"(c1), "l"(l2_stream()) : "memory");
}
__device__ __forceinline__ void tma3d_prefetch(const CUtensorMap* m, int c0, int c1, int c2) {
  asm volatile("cp.async.bulk.prefetch.tensor.3d.L2.global.tile [%0, {%1, %2, %3}];" ::"l"(m), "r"(c0), "r"(c1), "r"(c2) : "memory");
}
__device__ __forceinline__ void bulk_load(uint32_t dst, const void* src, uint32_t bytes, uint32_t bar) {
  asm volatile("cp.async.bulk.shared::cluster.global.mbarrier::complete_tx::bytes [%0], [%1], %2, [%3];" ::"r"(dst), "l"(src), "r"(bytes), "r"(bar) : "memory");
}
__device__ __forceinline__ void bulk_load_stream(uint32_t dst, const void* src, uint32_t bytes, uint32_t bar) {
  asm volatile("cp.async.bulk.shared::cluster.global.mbarrier::complete_tx::bytes.L2::cache_hint [%0], [%1], %2, [%3], %4;"
               ::"r"(dst), "l"(src), "r"(bytes), "r"(bar), "l"(l2_stream()) : "memory");
}
__device__ __forceinline__ void bulk_store(void* dst, uint32_t src, uint32_t bytes) {
  asm volatile("cp.async.bulk.global.shared::cta.bulk_group [%0], [%1], %2;" ::"l"(dst), "r"(src), "r"(bytes) : "memory");
}
__device__ __forceinline__ uint32_t unit_of(uint32_t table, uint32_t i) { return ((table >> (i * 4)) & 15) * UNIT; }
__device__ __forceinline__ void tma3d(uint32_t dst, const CUtensorMap* m, int c0, int c1, int c2, uint32_t bar) {
  asm volatile("cp.async.bulk.tensor.3d.shared::cluster.global.mbarrier::complete_tx::bytes.L2::cache_hint [%0], [%1, {%3, %4, %5}], [%2], %6;"
               ::"r"(dst), "l"(m), "r"(bar), "r"(c0), "r"(c1), "r"(c2), "l"(l2_stream()) : "memory");
}
template <bool STREAM>
__device__ __forceinline__ void tma3d_mc(uint32_t dst, const CUtensorMap* m, int c0, int c1, int c2, uint32_t bar) {
  if (STREAM)
    asm volatile("cp.async.bulk.tensor.3d.shared::cluster.global.mbarrier::complete_tx::bytes.multicast::cluster.L2::cache_hint [%0], [%1, {%3, %4, %5}], [%2], %6, %7;"
                 ::"r"(dst), "l"(m), "r"(bar), "r"(c0), "r"(c1), "r"(c2), "h"((uint16_t)3), "l"(l2_stream()) : "memory");
  else
    asm volatile("cp.async.bulk.tensor.3d.shared::cluster.global.mbarrier::complete_tx::bytes.multicast::cluster [%0], [%1, {%3, %4, %5}], [%2], %6;"
                 ::"r"(dst), "l"(m), "r"(bar), "r"(c0), "r"(c1), "r"(c2), "h"((uint16_t)3) : "memory");
}
__device__ __forceinline__ void prefetch_map(const CUtensorMap* m) {
  asm volatile("prefetch.tensormap [%0];" ::"l"(m) : "memory");
}
__device__ __forceinline__ void fence_async() { asm volatile("fence.proxy.async.global;" ::: "memory"); }
__device__ __forceinline__ void fence_async_smem() { asm volatile("fence.proxy.async.shared::cta;" ::: "memory"); }
__device__ __forceinline__ void bar_sync(int id, int n) { asm volatile("bar.sync %0, %1;" ::"r"(id), "r"(n) : "memory"); }
__device__ __forceinline__ void bar_arrive(int id, int n) { asm volatile("bar.arrive %0, %1;" ::"r"(id), "r"(n) : "memory"); }
__device__ __forceinline__ void wg_fence() { asm volatile("wgmma.fence.sync.aligned;" ::: "memory"); }
__device__ __forceinline__ void wg_commit() { asm volatile("wgmma.commit_group.sync.aligned;" ::: "memory"); }
template <int N> __device__ __forceinline__ void wg_wait() { asm volatile("wgmma.wait_group.sync.aligned %0;" ::"n"(N) : "memory"); }
__device__ __forceinline__ uint64_t make_desc(uint32_t addr, uint32_t lbo, uint32_t sbo) {
  return (uint64_t)((addr & 0x3FFFF) >> 4) | ((uint64_t)(lbo >> 4) << 16) | ((uint64_t)(sbo >> 4) << 32) | (1ull << 62);
}
__device__ __forceinline__ uint32_t ld_relaxed(const uint32_t* p) {
  uint32_t v; asm volatile("ld.relaxed.gpu.global.u32 %0, [%1];" : "=r"(v) : "l"(p) : "memory"); return v;
}
__device__ __forceinline__ uint32_t ld_acquire(const uint32_t* p) {
  uint32_t v; asm volatile("ld.acquire.gpu.global.u32 %0, [%1];" : "=r"(v) : "l"(p) : "memory"); return v;
}
__device__ __forceinline__ uint4 ld_relaxed4(const uint32_t* p) {
  uint4 v; asm volatile("ld.relaxed.gpu.global.v4.u32 {%0,%1,%2,%3}, [%4];" : "=r"(v.x), "=r"(v.y), "=r"(v.z), "=r"(v.w) : "l"(p) : "memory"); return v;
}
__device__ __forceinline__ uint2 ld_relaxed2(const uint32_t* p) {
  uint2 v; asm volatile("ld.relaxed.gpu.global.v2.u32 {%0,%1}, [%2];" : "=r"(v.x), "=r"(v.y) : "l"(p) : "memory"); return v;
}
__device__ __forceinline__ void st_relaxed(uint32_t* p, uint32_t v) {
  asm volatile("st.relaxed.gpu.global.u32 [%0], %1;" ::"l"(p), "r"(v) : "memory");
}
__device__ __forceinline__ void st_relaxed2(uint32_t* p, uint32_t a, uint32_t b) {
  asm volatile("st.relaxed.gpu.global.v2.u32 [%0], {%1,%2};" ::"l"(p), "r"(a), "r"(b) : "memory");
}
__device__ __forceinline__ void st_relaxed4(uint32_t* p, uint32_t a, uint32_t b, uint32_t c, uint32_t d) {
  asm volatile("st.relaxed.gpu.global.v4.u32 [%0], {%1,%2,%3,%4};" ::"l"(p), "r"(a), "r"(b), "r"(c), "r"(d) : "memory");
}
__device__ __forceinline__ void st_b128(uint32_t* p, uint32_t a, uint32_t b, uint32_t c, uint32_t d) {
  asm volatile("{ .reg .b64 u, v; .reg .b128 w; mov.b64 u, {%1, %2}; mov.b64 v, {%3, %4}; mov.b128 w, {u, v}; st.relaxed.gpu.global.b128 [%0], w; }"
               ::"l"(p), "r"(a), "r"(b), "r"(c), "r"(d) : "memory");
}
__device__ __forceinline__ uint4 ld_b128(const uint32_t* p) {
  uint4 r;
  asm volatile("{ .reg .b64 u, v; .reg .b128 w; ld.relaxed.gpu.global.b128 w, [%4]; mov.b128 {u, v}, w; mov.b64 {%0, %1}, u; mov.b64 {%2, %3}, v; }"
               : "=r"(r.x), "=r"(r.y), "=r"(r.z), "=r"(r.w) : "l"(p) : "memory");
  return r;
}
__device__ __forceinline__ void st_pairs(uint32_t* p, uint32_t a, uint32_t b, uint32_t tag) {
  asm volatile("{ .reg .b64 u, v; mov.b64 u, {%1, %3}; mov.b64 v, {%2, %3}; st.relaxed.gpu.global.v2.b64 [%0], {u, v}; }"
               ::"l"(p), "r"(a), "r"(b), "r"(tag) : "memory");
}
__device__ __forceinline__ uint4 ld_pairs(const uint32_t* p) {
  uint4 v;
  asm volatile("{ .reg .b64 u, v; ld.relaxed.gpu.global.v2.b64 {u, v}, [%4]; mov.b64 {%0, %1}, u; mov.b64 {%2, %3}, v; }"
               : "=r"(v.x), "=r"(v.y), "=r"(v.z), "=r"(v.w) : "l"(p) : "memory");
  return v;
}
__device__ __forceinline__ uint2 ld_pair(const uint32_t* p) {
  uint2 v;
  asm volatile("{ .reg .b64 u; ld.relaxed.gpu.global.b64 u, [%2]; mov.b64 {%0, %1}, u; }" : "=r"(v.x), "=r"(v.y) : "l"(p) : "memory");
  return v;
}
__device__ __forceinline__ void red_release(uint32_t* p, uint32_t v) {
  asm volatile("red.release.gpu.global.add.u32 [%0], %1;" ::"l"(p), "r"(v) : "memory");
}
__device__ __forceinline__ uint32_t ldg_nc1(const void* p) {
  uint32_t v;
  asm volatile("ld.global.nc.u32 %0, [%1];" : "=r"(v) : "l"(p));
  return v;
}
__device__ __forceinline__ uint4 ldg_nc4(const void* p) {
  uint4 v; asm volatile("ld.global.nc.L1::no_allocate.v4.u32 {%0,%1,%2,%3}, [%4];" : "=r"(v.x), "=r"(v.y), "=r"(v.z), "=r"(v.w) : "l"(p)); return v;
}
__device__ __forceinline__ void stg4(void* p, uint4 v) {
  asm volatile("st.global.v4.u32 [%0], {%1,%2,%3,%4};" ::"l"(p), "r"(v.x), "r"(v.y), "r"(v.z), "r"(v.w) : "memory");
}
__device__ __forceinline__ void wait_counter(const uint32_t* p, uint32_t target) {
  uint32_t n = 0;
  while ((int)(ld_acquire(p) - target) < 0) { watchdog(n); }
}
__device__ __forceinline__ uint32_t tagf(float v, uint32_t tag) { return (__float_as_uint(v) & ~3u) | tag; }
__device__ __forceinline__ bool tag_ok(uint4 v, uint32_t tag) { return (((v.x ^ tag) | (v.y ^ tag) | (v.z ^ tag) | (v.w ^ tag)) & 3u) == 0; }
__device__ __forceinline__ float untag_sum(uint32_t a, uint32_t b) { return __uint_as_float(a & ~3u) + __uint_as_float(b & ~3u); }
__device__ __forceinline__ uint4 poll4(const uint32_t* p, uint32_t tag) {
  uint4 v = ld_relaxed4(p);
  uint32_t n = 0;
  while (!tag_ok(v, tag)) { v = ld_relaxed4(p); watchdog(n); }
  return v;
}
__device__ __forceinline__ float bf_lo(uint32_t v) { return __uint_as_float(v << 16); }
__device__ __forceinline__ float bf_hi(uint32_t v) { return __uint_as_float(v & 0xffff0000u); }
__device__ __forceinline__ uint32_t pack_bf(float lo, float hi) {
  uint32_t r; asm("cvt.rn.bf16x2.f32 %0, %1, %2;" : "=r"(r) : "f"(hi), "f"(lo)); return r;
}
__device__ __forceinline__ float rbf(float v) { return __uint_as_float(pack_bf(0.f, v) & 0xffff0000u); }
__device__ __forceinline__ uint32_t hmul2(uint32_t a, uint32_t b) {
  uint32_t r; asm("mul.rn.bf16x2 %0, %1, %2;" : "=r"(r) : "r"(a), "r"(b)); return r;
}
__device__ __forceinline__ uint32_t hadd2(uint32_t a, uint32_t b) {
  uint32_t r; asm("add.rn.bf16x2 %0, %1, %2;" : "=r"(r) : "r"(a), "r"(b)); return r;
}
__device__ __forceinline__ uint32_t hsub2(uint32_t a, uint32_t b) {
  uint32_t r; asm("sub.rn.bf16x2 %0, %1, %2;" : "=r"(r) : "r"(a), "r"(b)); return r;
}
__device__ __forceinline__ uint32_t hmax2(uint32_t a, uint32_t b) {
  uint32_t r; asm("max.bf16x2 %0, %1, %2;" : "=r"(r) : "r"(a), "r"(b)); return r;
}
__device__ __forceinline__ float ex2(float x) { float r; asm("ex2.approx.ftz.f32 %0, %1;" : "=f"(r) : "f"(x)); return r; }
__device__ __forceinline__ void stmatrix4(uint32_t addr, uint32_t a, uint32_t b, uint32_t c, uint32_t d) {
  asm volatile("stmatrix.sync.aligned.m8n8.x4.shared.b16 [%0], {%1,%2,%3,%4};" ::"r"(addr), "r"(a), "r"(b), "r"(c), "r"(d) : "memory");
}
__device__ __forceinline__ void ldmatrix4(uint32_t addr, uint32_t& a, uint32_t& b, uint32_t& c, uint32_t& d) {
  asm volatile("ldmatrix.sync.aligned.m8n8.x4.shared.b16 {%0,%1,%2,%3}, [%4];" : "=r"(a), "=r"(b), "=r"(c), "=r"(d) : "r"(addr) : "memory");
}
__device__ __forceinline__ void ldmatrix4t(uint32_t addr, uint32_t& a, uint32_t& b, uint32_t& c, uint32_t& d) {
  asm volatile("ldmatrix.sync.aligned.m8n8.x4.trans.shared.b16 {%0,%1,%2,%3}, [%4];" : "=r"(a), "=r"(b), "=r"(c), "=r"(d) : "r"(addr) : "memory");
}
__device__ __forceinline__ void mma16816(float (&d)[4], uint32_t a0, uint32_t a1, uint32_t a2, uint32_t a3, uint32_t b0, uint32_t b1) {
  asm volatile("mma.sync.aligned.m16n8k16.row.col.f32.bf16.bf16.f32 {%0,%1,%2,%3}, {%4,%5,%6,%7}, {%8,%9}, {%0,%1,%2,%3};"
               : "+f"(d[0]), "+f"(d[1]), "+f"(d[2]), "+f"(d[3]) : "r"(a0), "r"(a1), "r"(a2), "r"(a3), "r"(b0), "r"(b1));
}
__device__ __forceinline__ void sts1(uint32_t a, uint32_t v) { asm volatile("st.shared.u32 [%0], %1;" ::"r"(a), "r"(v) : "memory"); }
__device__ __forceinline__ uint4 lds4(uint32_t a) {
  uint4 v; asm volatile("ld.shared.v4.u32 {%0,%1,%2,%3}, [%4];" : "=r"(v.x), "=r"(v.y), "=r"(v.z), "=r"(v.w) : "r"(a) : "memory"); return v;
}
__device__ __forceinline__ uint2 lds2(uint32_t a) {
  uint2 v; asm volatile("ld.shared.v2.u32 {%0,%1}, [%2];" : "=r"(v.x), "=r"(v.y) : "r"(a) : "memory"); return v;
}
__device__ __forceinline__ uint32_t lds1(uint32_t a) {
  uint32_t v; asm volatile("ld.shared.u32 %0, [%1];" : "=r"(v) : "r"(a) : "memory"); return v;
}
__device__ __forceinline__ void sts2(uint32_t a, uint32_t x, uint32_t y) { asm volatile("st.shared.v2.u32 [%0], {%1,%2};" ::"r"(a), "r"(x), "r"(y) : "memory"); }
__device__ __forceinline__ void sts4(uint32_t a, uint4 v) {
  asm volatile("st.shared.v4.u32 [%0], {%1,%2,%3,%4};" ::"r"(a), "r"(v.x), "r"(v.y), "r"(v.z), "r"(v.w) : "memory");
}
__device__ __forceinline__ float silu_f(float v) { return __fdividef(v, 1.f + __expf(-v)); }
__device__ __forceinline__ uint32_t hfma2(uint32_t a, uint32_t b, uint32_t c) {
  uint32_t r; asm("fma.rn.bf16x2 %0, %1, %2, %3;" : "=r"(r) : "r"(a), "r"(b), "r"(c)); return r;
}
__device__ __forceinline__ void split_inv(float sd, uint32_t& ih, uint32_t& il) {
  const float inv = 1.f / sd;
  ih = pack_bf(inv, inv);
  const float lo = inv - bf_lo(ih);
  il = pack_bf(lo, lo);
}
__device__ __forceinline__ uint32_t ln_mod(uint32_t x, uint32_t mean2, uint32_t ih, uint32_t il, uint32_t c1, uint32_t sh) {
  const uint32_t d = hsub2(x, mean2);
  return hadd2(hmul2(hfma2(d, ih, hmul2(d, il)), c1), sh);
}

#define R8(a, i) "+f"(a[i]), "+f"(a[i + 1]), "+f"(a[i + 2]), "+f"(a[i + 3]), "+f"(a[i + 4]), "+f"(a[i + 5]), "+f"(a[i + 6]), "+f"(a[i + 7])
#define D64 "{%0,%1,%2,%3,%4,%5,%6,%7,%8,%9,%10,%11,%12,%13,%14,%15,%16,%17,%18,%19,%20,%21,%22,%23,%24,%25,%26,%27,%28,%29,%30,%31," \
            "%32,%33,%34,%35,%36,%37,%38,%39,%40,%41,%42,%43,%44,%45,%46,%47,%48,%49,%50,%51,%52,%53,%54,%55,%56,%57,%58,%59,%60,%61,%62,%63}"
template <int TB>
__device__ __forceinline__ void mma_ss(float (&d)[64], uint64_t da, uint64_t db, int sc) {
  asm volatile("{\n.reg .pred p;\nsetp.ne.b32 p, %66, 0;\n"
               "wgmma.mma_async.sync.aligned.m64n128k16.f32.bf16.bf16 " D64 ", %64, %65, p, 1, 1, 0, %67;\n}"
               : R8(d, 0), R8(d, 8), R8(d, 16), R8(d, 24), R8(d, 32), R8(d, 40), R8(d, 48), R8(d, 56)
               : "l"(da), "l"(db), "r"(sc), "n"(TB));
}
template <int TB>
__device__ __forceinline__ void mma_rs(float (&d)[64], uint32_t a0, uint32_t a1, uint32_t a2, uint32_t a3, uint64_t db, int sc) {
  asm volatile("{\n.reg .pred p;\nsetp.ne.b32 p, %69, 0;\n"
               "wgmma.mma_async.sync.aligned.m64n128k16.f32.bf16.bf16 " D64 ", {%64,%65,%66,%67}, %68, p, 1, 1, %70;\n}"
               : R8(d, 0), R8(d, 8), R8(d, 16), R8(d, 24), R8(d, 32), R8(d, 40), R8(d, 48), R8(d, 56)
               : "r"(a0), "r"(a1), "r"(a2), "r"(a3), "l"(db), "r"(sc), "n"(TB));
}
#define D128 "{%0,%1,%2,%3,%4,%5,%6,%7,%8,%9,%10,%11,%12,%13,%14,%15,%16,%17,%18,%19,%20,%21,%22,%23,%24,%25,%26,%27,%28,%29,%30,%31," \
             "%32,%33,%34,%35,%36,%37,%38,%39,%40,%41,%42,%43,%44,%45,%46,%47,%48,%49,%50,%51,%52,%53,%54,%55,%56,%57,%58,%59,%60,%61,%62,%63," \
             "%64,%65,%66,%67,%68,%69,%70,%71,%72,%73,%74,%75,%76,%77,%78,%79,%80,%81,%82,%83,%84,%85,%86,%87,%88,%89,%90,%91,%92,%93,%94,%95," \
             "%96,%97,%98,%99,%100,%101,%102,%103,%104,%105,%106,%107,%108,%109,%110,%111,%112,%113,%114,%115,%116,%117,%118,%119,%120,%121,%122,%123,%124,%125,%126,%127}"
#define R128(d, e) R8(d, 0), R8(d, 8), R8(d, 16), R8(d, 24), R8(d, 32), R8(d, 40), R8(d, 48), R8(d, 56), \
                   R8(e, 0), R8(e, 8), R8(e, 16), R8(e, 24), R8(e, 32), R8(e, 40), R8(e, 48), R8(e, 56)
__device__ __forceinline__ void mma256_ss(float (&d)[64], float (&e)[64], uint64_t da, uint64_t db, int sc) {
  asm volatile("{\n.reg .pred p;\nsetp.ne.b32 p, %130, 0;\n"
               "wgmma.mma_async.sync.aligned.m64n256k16.f32.bf16.bf16 " D128 ", %128, %129, p, 1, 1, 0, 1;\n}"
               : R128(d, e) : "l"(da), "l"(db), "r"(sc));
}
__device__ __forceinline__ void mma256_rs(float (&d)[64], float (&e)[64], uint32_t a0, uint32_t a1, uint32_t a2, uint32_t a3, uint64_t db) {
  asm volatile("{\n.reg .pred p;\nsetp.ne.b32 p, 1, 0;\n"
               "wgmma.mma_async.sync.aligned.m64n256k16.f32.bf16.bf16 " D128 ", {%128,%129,%130,%131}, %132, p, 1, 1, 1;\n}"
               : R128(d, e) : "r"(a0), "r"(a1), "r"(a2), "r"(a3), "l"(db));
}
template <int N> __device__ __forceinline__ void keep(float (&a)[N]) {
#pragma unroll
  for (int i = 0; i < N; i++) asm volatile("" : "+f"(a[i])::"memory");
}
template <int N> __device__ __forceinline__ void keep(uint32_t (&a)[N]) {
#pragma unroll
  for (int i = 0; i < N; i++) asm volatile("" : "+r"(a[i])::"memory");
}

#define PROF(grp, cond, idx) do {} while (0)

constexpr float SCL2 = 1.4426950408889634f * 0.08838834764831845f;

__device__ __forceinline__ void pack_p(const float (&s)[64], uint32_t (&p)[32]) {
#pragma unroll
  for (int i = 0; i < 32; i++) p[i] = pack_bf(s[2 * i], s[2 * i + 1]);
}

__device__ __forceinline__ void issue_qk(float (&s)[64], uint32_t q0, uint32_t q1, uint32_t kslot) {
  const uint64_t db = make_desc(kslot, 16, 1024), da0 = make_desc(q0, 16, 1024), da1 = make_desc(q1, 16, 1024);
#pragma unroll
  for (int kk = 0; kk < 8; kk++) mma_ss<0>(s, (kk < 4 ? da0 : da1) + (kk & 3) * 2, db + (kk >> 2) * 1024 + (kk & 3) * 2, kk != 0);
}
__device__ __forceinline__ void issue_pv(float (&o)[64], uint32_t (&p)[32], uint32_t vslot, int acc) {
  uint64_t db = make_desc(vslot, 16384, 1024);
#pragma unroll
  for (int kk = 0; kk < 8; kk++)
    mma_rs<1>(o, p[4 * kk], p[4 * kk + 1], p[4 * kk + 2], p[4 * kk + 3], db + kk * 128, kk == 0 ? acc : 1);
}

template <int H>
__device__ __forceinline__ void store_chunk(const float (&a)[64], uint32_t addr) {
#pragma unroll
  for (int i = 8 * H; i < 8 * H + 8; i += 2)
    stmatrix4(addr ^ ((i & 7) << 4), pack_bf(a[4 * i], a[4 * i + 1]), pack_bf(a[4 * i + 2], a[4 * i + 3]),
              pack_bf(a[4 * i + 4], a[4 * i + 5]), pack_bf(a[4 * i + 6], a[4 * i + 7]));
}
template <int H>
__device__ __forceinline__ void store_chunk(const float (&a)[64], float i0, float i1, uint32_t addr) {
#pragma unroll
  for (int i = 8 * H; i < 8 * H + 8; i += 2)
    stmatrix4(addr ^ ((i & 7) << 4), pack_bf(a[4 * i] * i0, a[4 * i + 1] * i0), pack_bf(a[4 * i + 2] * i1, a[4 * i + 3] * i1),
              pack_bf(a[4 * i + 4] * i0, a[4 * i + 5] * i0), pack_bf(a[4 * i + 6] * i1, a[4 * i + 7] * i1));
}
__device__ __forceinline__ float inv_quad_sum(float l) {
  l += __shfl_xor_sync(0xffffffffu, l, 1);
  l += __shfl_xor_sync(0xffffffffu, l, 2);
  return __fdividef(1.f, l);
}

__device__ __forceinline__ void ln_scalars(float mean, float var, float& mb, float& sd) {
  mb = rbf(mean);
  sd = rbf(sqrtf(rbf(rbf(var) + 1e-5f)));
}

__global__ void __cluster_dims__(2, 1, 1) __launch_bounds__(384, 1) fused_kernel(const __grid_constant__ Maps maps, const Ptrs P) {
  extern __shared__ __align__(1024) uint8_t smem_raw[];
  const uint32_t base = smem_u32(smem_raw);
  const int tid = threadIdx.x, lane = tid & 31;
  const int warp = __shfl_sync(0xffffffffu, tid >> 5, 0);
  const int b = blockIdx.x;
  PROF(15, tid == 0, 0);

  if (b >= NMAIN) {
    float* sc = reinterpret_cast<float*>(smem_raw);
    float* red = sc + DM;
    for (int k = tid; k < DM; k += 384) sc[k] = rbf(silu_f(__bfloat162float(P.c[k])));
    __syncthreads();
    if (tid < 256) {
      const int col = 2048 + (b - NMAIN) * 1024 + (tid & 127) * 8, r0 = (tid >> 7) * 512;
      float acc[8];
#pragma unroll
      for (int e = 0; e < 8; e++) acc[e] = 0.f;
#pragma unroll 1
      for (int r = r0; r < r0 + 512; r += HU) {
        uint4 w[HU];
#pragma unroll
        for (int u = 0; u < HU; u++) w[u] = ldg_nc4(P.w_mod + (size_t)(r + u) * NMOD + col);
#pragma unroll
        for (int u = 0; u < HU; u++) {
          float s = sc[r + u];
          acc[0] += s * bf_lo(w[u].x); acc[1] += s * bf_hi(w[u].x); acc[2] += s * bf_lo(w[u].y); acc[3] += s * bf_hi(w[u].y);
          acc[4] += s * bf_lo(w[u].z); acc[5] += s * bf_hi(w[u].z); acc[6] += s * bf_lo(w[u].w); acc[7] += s * bf_hi(w[u].w);
        }
      }
      if (tid >= 128) {
#pragma unroll
        for (int e = 0; e < 8; e++) red[(tid & 127) * 8 + e] = acc[e];
      }
      const uint32_t tag = ld_relaxed(&g_epoch) % 3 + 1;
      bar_sync(1, 256);
      if (tid < 128) {
        uint32_t o[8];
#pragma unroll
        for (int e = 0; e < 8; e++) o[e] = __float_as_uint(rbf(acc[e] + red[tid * 8 + e])) | tag;
        st_relaxed4(g_mod + col, o[0], o[1], o[2], o[3]);
        st_relaxed4(g_mod + col + 4, o[4], o[5], o[6], o[7]);
      }
    }
    PROF(2, tid == 0, 1);
    return;
  }

  const int rank = b & 1;
  const int rb = ((b >> 4) << 1) | rank, cj = (b >> 1) & 7;
  const uint32_t bfull = base + OFF_BAR, bempty = bfull + NSLOT * 8;
  const uint32_t gfull = bempty + NSLOT * 8, gempty = gfull + 32;
  const uint32_t bar_ofull = gempty + 32;
  const uint32_t bar_ofree = bar_ofull + 16;
  const uint32_t bar_par = bar_ofree + 32;
  const uint32_t bar_mod = bar_par + 8;
  const uint32_t bar_pread = bar_mod + 8;
  const uint32_t bar_xres = bar_pread + 8;
  const uint32_t bar_w1 = bar_xres + 8;
  const uint32_t bar_w2 = bar_w1 + 8;
  const uint32_t bar_last = bar_w2 + 8;
  const uint32_t bar_ring = bar_last + 16;
  const uint32_t bar_box = bar_ring + 8;
  const uint32_t bar_go = bar_box + 96;
  const uint32_t bar_go2 = bar_go + 16;
  const uint32_t bar_cnt = bar_go + 24;
  const uint32_t xfull = bar_go + 32, xempty = xfull + 32;
  const uint32_t bar_hw = xempty + 32, bar_hx = bar_hw + 8;
  const uint32_t bar_hpub = bar_hx + 16;
  const uint32_t bar_ring0 = bar_hpub + 8;
  const uint32_t bar_res = bar_ring0 + 8;
  const uint32_t bar_rst = bar_go + 8;
  const uint32_t stage = base + OFF_STAGE, par = base + OFF_PAR;

  if (warp == 8 && elect_one()) {
    for (int s = 0; s < NSLOT; s++) { mbar_init(bfull + s * 8, 1); mbar_init(bempty + s * 8, 16); }
    for (int s = 0; s < 4; s++) { mbar_init(gfull + s * 8, 1); mbar_init(gempty + s * 8, 16); mbar_init(xfull + s * 8, 1); mbar_init(xempty + s * 8, 8); mbar_init(bar_ofree + s * 8, 1); }
    mbar_init(bar_ofull, 128); mbar_init(bar_ofull + 8, 128);
    mbar_init(bar_par, 64); mbar_init(bar_mod, 256); mbar_init(bar_pread, 8); mbar_init(bar_xres, 1);
    mbar_init(bar_w1, 1); mbar_init(bar_w2, 1); mbar_init(bar_last, 1); mbar_init(bar_last + 8, 1); mbar_init(bar_ring, 8); mbar_init(bar_go, 1); mbar_init(bar_go2, 1); mbar_init(bar_cnt, 1); mbar_init(bar_rst, 64); mbar_init(bar_hpub, 8); mbar_init(bar_ring0, 8); mbar_init(bar_res, 1);
    for (int s = 0; s < 12; s++) mbar_init(bar_box + s * 8, 1);
    asm volatile("fence.mbarrier_init.release.cluster;" ::: "memory");
    prefetch_map(&maps.x); prefetch_map(&maps.wq); prefetch_map(&maps.k); prefetch_map(&maps.v);
  }
  if (warp == 9 && elect_one()) {
    mbar_init(bar_hw, 1); mbar_init(bar_hx, 1); mbar_init(bar_hx + 8, 1);
    asm volatile("fence.mbarrier_init.release.cluster;" ::: "memory");
    mbar_expect_tx(bar_hw, 32768);
    mbar_expect_tx(bar_hx, 16384);
    mbar_expect_tx(bar_hx + 8, 16384);
    const __nv_bfloat16* xs = P.x + (size_t)(rb * 128 + cj * 16) * DM;
    bulk_load(base + 2 * GST_BYTES, xs, 16384, bar_hx);
    tma2d(stage, &maps.wm, (b >> 1) * 32, rank * 512, bar_hw);
    tma2d(stage + 16384, &maps.wm, (b >> 1) * 32, rank * 512 + 256, bar_hw);
    bulk_load(base + 3 * GST_BYTES, xs + 8 * DM, 16384, bar_hx + 8);
  }
  cluster_arrive();

  if (warp >= 8) {
    asm volatile("setmaxnreg.dec.sync.aligned.u32 40;");
    if (warp < 10) bar_arrive(1, 320);
    cluster_wait();
    if (warp == 8) {
      const int kvrow = (cj >> 1) * SK + (SK - WIN);
      int wch = cj * 8 + rank * 2;
#pragma unroll 1
      for (int ps = 0; ps < 3; ps++) {
        const CUtensorMap* mw = ps == 2 ? &maps.wo : &maps.wq;
        const uint32_t xt = ps == 1 ? XT1 : XT2, wt = ps == 0 ? WT0 : (ps == 1 ? WT1 : WT2);
        const int nst = ps == 2 ? 32 : 16;
        if (ps) {
          mbar_wait(bar_ofree + (ps - 1) * 16, 0);
          fence_async();
        }
#pragma unroll 1
        for (int i = 0; i < nst; i++) {
          const uint32_t bf = i < 30 ? gfull + (i & 3) * 8 : bar_last + (i & 1) * 8;
          const int kt = ps == 2 ? (((cj & 1) * 4 + ((i >> 1) & 3)) * 4 + (i >> 3)) * 2 + (i & 1) : (i + (ps ? 0 : b & 14)) & 15;
          const uint32_t wd = base + unit_of(wt, i & 3) + rank * UNIT, xd = base + unit_of(xt, i & 3);
          const uint8_t* xs = g_act + (uint32_t)(rb * 80 + (ps - 1) * 16 + kt) * UNIT;
          if (ps == 0 && i == HD) mbar_wait(bar_mod, 0);
          if (ps && i && i < 4) mbar_wait(bempty + (i == 3 ? 3 : i - 1) * 8, 1);
          mbar_wait(gempty + (i & 3) * 8, ((i >> 2) & 1) ^ 1);
          if (elect_one()) {
            mbar_expect_tx(bf, ps ? GST_BYTES : 2 * UNIT);
            tma3d_mc<true>(wd, mw, 0, kt * 64, wch, bf);
          }
          if (ps) {
            if (i == 16) mbar_wait(bar_cnt, 0);
            if (i == 2) mbar_wait(bempty + 16, 1);
            if (elect_one()) {
              bulk_load_stream(xd, xs, UNIT, bf);
              mbar_arrive_pred(ps == 1 ? bar_go2 : bar_go, i == (ps == 1 ? 15 : GOST - 1));
              mbar_arrive_pred(bar_res, ((1u << RES0 | 1u << RES1) >> i) & 1);
            }
          }
        }
        if (ps == 2) break;
        wch = ps ? ((wch >> 3) ^ rank) * 2 : wch + 4;
#pragma unroll 1
        for (int u = 0; u < 16; u++) {
          const bool isk = (u == 0) || ((u & 1) && u < 15);
          const int blk = (isk ? (u + 1) >> 1 : (u == 15 ? 7 : (u >> 1) - 1)) & 3;
          const uint32_t sl = base + unit_of(ps ? AT1 : AT0, u & 3) + rank * UNIT, bf = bfull + (u & 3) * 8;
          if (u < 4) mbar_wait(gempty + ((u + 1) >> 1) * 8, 1);
          mbar_wait(bempty + (u & 3) * 8, ((u >> 2) & 1) ^ 1);
          if (elect_one()) {
            mbar_expect_tx(bf, SLOT_BYTES);
            tma3d_mc<false>(sl, isk ? &maps.k : &maps.v, 0, kvrow + blk * 128, rank, bf);
          }
        }
      }
      if (b < NFFN) {
        mbar_wait(bar_ring0, 0);
#pragma unroll 1
        for (int u = 0; u < 12 + FPACE; u++) {
          if (u == E0) mbar_wait(bar_ring, 0);
          if (u >= FPACE) mbar_wait(bar_box + (u - FPACE) * 8, 0);
          if (elect_one()) {
            if (u - FPACE == 7) { mbar_arrive(bar_w1); PROF(8, true, 59); }
            if (u - FPACE == 11) { mbar_arrive(bar_w2); PROF(8, true, 60); }
            if (u < 12) {
              mbar_expect_tx(bar_box + u * 8, UNIT);
              if (u < 8) tma2d(base + OFF_GATE + u * UNIT, u < 4 ? &maps.wg : &maps.wu, b * 32, (u & 3) * 256, bar_box + u * 8);
              else tma3d(base + (u - 8) * UNIT, &maps.wd, 0, b * 32, (u - 8) * 4, bar_box + u * 8);
            }
          }
        }
      }
    } else if (warp == 9) {
      const uint32_t target = 8 * (ld_relaxed(&g_epoch) + 1);
#pragma unroll 1
      for (int i = 0; i < 16; i++) {
        if (i == HDX) mbar_wait(bar_mod, 0);
        if (i == NRS) {
          wait_counter(&g_cnt_h[rb * 32], target);
          PROF(1, lane == 0, 26);
          fence_async();
        }
        mbar_wait(xempty + (i & 3) * 8, ((i >> 2) & 1) ^ 1);
        if (elect_one()) {
          mbar_expect_tx(xfull + (i & 3) * 8, UNIT);
          if (i < NRS) tma2d(base + (i & 3) * GST_BYTES, &maps.x, ((2 * cj + i) & 15) * 64, rb * 128, xfull + (i & 3) * 8);
          else bulk_load_stream(base + (i & 3) * GST_BYTES, g_act + (uint32_t)(rb * 80 + ((2 * cj + i) & 15)) * UNIT, UNIT, xfull + (i & 3) * 8);
        }
      }
      prefetch_map(&maps.wo);
#pragma unroll 1
      for (int t = 0; t < 4; t++) {
#pragma unroll 1
        for (int w = 0; w < 2; w++) {
          mbar_wait(bar_ofull + w * 8, t & 1);
          uint8_t* dst = g_act + (uint32_t)(rb * 80 + 16 + (cj * 4 + t) * 2) * UNIT + w * 8192;
          if (elect_one()) {
            bulk_store(dst, base + unit_of(QT, 2 * t) + w * 8192, 8192);
            bulk_store(dst + UNIT, base + unit_of(QT, 2 * t + 1) + w * 8192, 8192);
            asm volatile("cp.async.bulk.commit_group;" ::: "memory");
          }
        }
        if (elect_one()) {
          asm volatile("cp.async.bulk.wait_group.read 0;" ::: "memory");
          mbar_arrive(bar_ofree + t * 8);
          asm volatile("cp.async.bulk.wait_group 0;" ::: "memory");
          fence_async();
          red_release(&g_cnt_o[((rb * 4 + t) * 2 + (cj >> 2)) * 32], 2);
          if (t == PF2T) for (int u = 0; u < PF2; u++)
            tma3d_prefetch(&maps.wo, 0, ((((cj & 1) * 4 + (b >> 5)) * 4 + u) * 2 + ((b >> 4) & 1)) * 64, (cj ^ rank) * 2);
        }
        if (t & 1) {
          wait_counter(&g_cnt_o[(rb * 8 + 2 * t - 2 + (cj & 1)) * 32], target);
          wait_counter(&g_cnt_o[(rb * 8 + 2 * t + (cj & 1)) * 32], target);
        }
      }
      fence_async();
      if (elect_one()) {
        mbar_arrive(bar_cnt);
        PROF(2, true, 27);
        mbar_expect_tx(bar_xres, 32768);
      }
#pragma unroll 1
      for (int u = 0; u < 2; u++) {
        mbar_wait(bar_res, u);
        if (elect_one()) tma2d(base + OFF_RES + u * UNIT, &maps.x, cj * 128 + u * 64, rb * 128, bar_xres);
      }
      mbar_wait(bar_last, 0);
      bar_arrive(8, 160); bar_arrive(9, 160);
      mbar_wait(bar_last + 8, 0);
      bar_arrive(10, 160); bar_arrive(11, 160);
    } else {
      const int t2 = tid - 320;
      if (t2 == 0) {
        mbar_wait(bar_hpub, 0);
        PROF(1, true, 24);
        red_release(&g_cnt_h[rb * 32], 1);
        PROF(1, true, 25);
        prefetch_map(&maps.wg); prefetch_map(&maps.wu); prefetch_map(&maps.wd);
      }
      __syncwarp();
      if (b < NFFN) {
        mbar_wait(bar_go2, 0);
        const __nv_bfloat16* pg = ((b & 1) ? P.w_up : P.w_gate) + (b >> 1) * 64 + (size_t)t2 * FF;
        const __nv_bfloat16* pd = P.w_down + (size_t)b * 32768 + t2 * 64;
        PROF(2, t2 == 0, 13);
#pragma unroll 1
        for (int i = 0; i < WN; i += WB) {
          uint32_t v[WB];
#pragma unroll
          for (int u = 0; u < WB; u++)
            asm volatile("ld.global.cg.L2::128B.u32 %0, [%1];" : "=r"(v[u]) : "l"(i < 16 ? pg + (size_t)(i + u) * 64 * FF : pd + (i + u - 16) * 4096));
#pragma unroll
          for (int u = 1; u < WB; u++) v[0] ^= v[u];
          sts1(par + PAR_SINK + t2 * 4, v[0]);
        }
        PROF(2, t2 == 0, 14);
      }
      const uint32_t epoch = ld_relaxed(&g_epoch), tag = epoch % 3 + 1;
      mbar_wait(bar_xres, 0);
      float s1 = 0.f, s2 = 0.f;
#pragma unroll 1
      for (int q = 0; q < 4; q++) {
        const int col = q * 256 + t2 * 4;
        uint4 vsb = poll4(g_mod + 3 * DM + col, tag), vcb = poll4(g_mod + 4 * DM + col, tag);
        uint2 wr = *reinterpret_cast<const uint2*>(P.w_r + col);
        float c0 = rbf(1.f + bf_hi(vcb.x)), c1 = rbf(1.f + bf_hi(vcb.y)), c2 = rbf(1.f + bf_hi(vcb.z)), c3 = rbf(1.f + bf_hi(vcb.w));
        float a0 = c0 * bf_lo(wr.x), a1 = c1 * bf_hi(wr.x), a2 = c2 * bf_lo(wr.y), a3 = c3 * bf_hi(wr.y);
        s1 += (a0 + a1) + (a2 + a3);
        s2 += bf_hi(vsb.x) * bf_lo(wr.x) + bf_hi(vsb.y) * bf_hi(wr.x) + bf_hi(vsb.z) * bf_lo(wr.y) + bf_hi(vsb.w) * bf_hi(wr.y);
        if ((col >> 7) == cj) {
          const int lc = col & 127;
          uint4 vga = poll4(g_mod + 2 * DM + col, tag), vgb = poll4(g_mod + 5 * DM + col, tag);
          sts2(par + PAR_GA + lc * 2, __byte_perm(vga.x, vga.y, 0x7632), __byte_perm(vga.z, vga.w, 0x7632));
          sts2(par + PAR_GB + lc * 2, __byte_perm(vgb.x, vgb.y, 0x7632), __byte_perm(vgb.z, vgb.w, 0x7632));
          sts2(par + PAR_SB + lc * 2, __byte_perm(vsb.x, vsb.y, 0x7632), __byte_perm(vsb.z, vsb.w, 0x7632));
          sts2(par + PAR_CB1 + lc * 2, pack_bf(c0, c1), pack_bf(c2, c3));
          sts4(par + PAR_A + lc * 4, make_uint4(__float_as_uint(a0), __float_as_uint(a1), __float_as_uint(a2), __float_as_uint(a3)));
        }
      }
#pragma unroll
      for (int o = 16; o > 0; o >>= 1) { s1 += __shfl_xor_sync(0xffffffffu, s1, o); s2 += __shfl_xor_sync(0xffffffffu, s2, o); }
      if (lane == 0) { sts2(par + PAR_CONST + (warp - 10) * 8, __float_as_uint(s1), __float_as_uint(s2)); sts1(par + PAR_CONST + 48, epoch); }
      if (t2 < 2) {
        uint4 g = poll4(g_mod + 5 * DM + b * 8 + t2 * 4, tag);
        sts4(par + PAR_CONST + 16 + t2 * 16, g);
      }
      mbar_wait(bar_go, 0);
      for (int q = XR; q < XE; q++) st_b128(g_xch + ((size_t)b * 8 * 256 + q * 64 + t2) * 4, (epoch & 1) << 16, 0, 0, 0);
      for (int q = 0; q < 2; q++) st_relaxed4(g_stats + ((size_t)cj * SEQ + rb * 128 + q * 64 + t2) * 4, 0, 0, 0, 0);
      __threadfence();
      mbar_arrive(bar_par);
      mbar_wait(bar_ring, 0);
      if (b < NFFN)
        for (int q = 0; q < 4; q++) st_relaxed4(g_ypart + ((size_t)(q * 32 + (t2 >> 1)) * NFFN + b) * 8 + (t2 & 1) * 4, 0, 0, 0, 0);
      st_relaxed4(g_row + rb * 2 * DM + (t2 >> 5) * DM + cj * 128 + (t2 & 31) * 4, 0, 0, 0, 0);
      if (cj == 0 && t2 < 2) st_relaxed4(g_cand + rb * 8 + t2 * 4, 0, 0, 0, 0);
      __threadfence();
      mbar_arrive(bar_rst);
    }
    __syncwarp();
    cluster_arrive();
    cluster_wait();
  } else {
    const int wg = warp >> 2;

    uint32_t tag;
    {
      uint32_t* const pmod = g_modp + rank * 2 * DM + (b >> 1) * 32 + lane;
      uint32_t* const pln = g_ln1 + (rb * 128 + cj * 16 + warp) * 4;
      const uint32_t cv = ldg_nc1(P.c + rank * 512 + tid * 2);
      const uint32_t epoch = ld_relaxed(&g_epoch);
      if (warp == 0) st_relaxed(pmod, 0);
      if (lane == 0) { st_relaxed2(pln, 0, 0); st_relaxed2(pln + 32, 0, 0); }
      asm volatile("setmaxnreg.inc.sync.aligned.u32 232;");
      sts1(par + tid * 4, pack_bf(silu_f(bf_lo(cv)), silu_f(bf_hi(cv))));
      bar_sync(1, 320);
      tag = epoch % 3 + 1;
#pragma unroll
      for (int part = 0; part < 3; part++) {
        if (part != 1) {
          const uint32_t xa = base + (2 + part / 2) * GST_BYTES + warp * 2048 + lane * 16;
          mbar_wait(bar_hx + part * 4, 0);
          float s0 = 0.f, s1 = 0.f, q0 = 0.f, q1 = 0.f;
#pragma unroll
          for (int q = 0; q < 4; q++) {
            const uint4 xv = lds4(xa + q * 512);
            const uint32_t u[4] = {xv.x, xv.y, xv.z, xv.w};
#pragma unroll
            for (int e = 0; e < 4; e++) { const float lo = bf_lo(u[e]), hi = bf_hi(u[e]); s0 += lo; s1 += hi; q0 += lo * lo; q1 += hi * hi; }
          }
          s0 += s1; q0 += q1;
#pragma unroll
          for (int o = 16; o > 0; o >>= 1) { s0 += __shfl_xor_sync(0xffffffffu, s0, o); q0 += __shfl_xor_sync(0xffffffffu, q0, o); }
          const float mean = s0 * (1.f / DM);
          float mb, sd;
          ln_scalars(mean, fmaxf(q0 * (1.f / DM) - mean * mean, 0.f), mb, sd);
          if (lane == 0) st_relaxed2(pln + part * 16, __float_as_uint(mb) | tag, __float_as_uint(sd) | tag);
          PROF(1, tid == 0 && part == 2, 4);
        } else {
          float acc[8];
#pragma unroll
          for (int e = 0; e < 8; e++) acc[e] = 0.f;
          const uint32_t wa = stage + (tid >> 2) * 64 + (((tid ^ (tid >> 3)) & 3) << 4), sa = par + (tid >> 3) * 4, sh = (tid & 4) ? 0x3244 : 0x1044;
          mbar_wait(bar_hw, 0);
#pragma unroll
          for (int p = 0; p < 8; p++) {
            const uint4 w = lds4(wa + p * 4096);
            const float s = __uint_as_float(__byte_perm(lds1(sa + p * 128), 0, sh));
            acc[0] += s * bf_lo(w.x); acc[1] += s * bf_hi(w.x); acc[2] += s * bf_lo(w.y); acc[3] += s * bf_hi(w.y);
            acc[4] += s * bf_lo(w.z); acc[5] += s * bf_hi(w.z); acc[6] += s * bf_lo(w.w); acc[7] += s * bf_hi(w.w);
          }
#pragma unroll
          for (int e = 0; e < 4; e++) {
            const bool up = lane & 16;
            acc[e] = (up ? acc[e + 4] : acc[e]) + __shfl_xor_sync(0xffffffffu, up ? acc[e] : acc[e + 4], 16);
          }
#pragma unroll
          for (int e = 0; e < 2; e++) {
            const bool up = lane & 8;
            acc[e] = (up ? acc[e + 2] : acc[e]) + __shfl_xor_sync(0xffffffffu, up ? acc[e] : acc[e + 2], 8);
          }
          {
            const bool up = lane & 4;
            acc[0] = (up ? acc[1] : acc[0]) + __shfl_xor_sync(0xffffffffu, up ? acc[0] : acc[1], 4);
          }
          sts1(par + 1024 + warp * 128 + ((lane & 3) * 8 + (lane >> 2)) * 4, __float_as_uint(acc[0]));
          bar_sync(1, 256);
          if (warp == 0) {
            float s = 0.f;
#pragma unroll
            for (int w8 = 0; w8 < 8; w8++) s += __uint_as_float(lds1(par + 1024 + w8 * 128 + lane * 4));
            st_relaxed(pmod, (__float_as_uint(s) & ~3u) | tag);
          }
          PROF(1, tid == 0, 3);
        }
      }
      {
        uint2 s0 = ld_relaxed2(g_ln1 + (rb * 128 + (tid & 127)) * 4);
        uint4 v[4];
#pragma unroll
        for (int q = 0; q < 4; q++) v[q] = ld_relaxed4(g_modp + q * DM + tid * 4);
        {
          uint32_t n = 0;
          while (!(tag_ok(v[0], tag) && tag_ok(v[1], tag) && tag_ok(v[2], tag) && tag_ok(v[3], tag))) {
#pragma unroll
            for (int q = 0; q < 4; q++)
              if (!tag_ok(v[q], tag)) v[q] = ld_relaxed4(g_modp + q * DM + tid * 4);
            if (((s0.x ^ tag) | (s0.y ^ tag)) & 3u) s0 = ld_relaxed2(g_ln1 + (rb * 128 + (tid & 127)) * 4);
            watchdog(n);
          }
        }
        const uint32_t d = stage + (tid >> 2) * 64 + (tid & 1) * 32 + (tid & 2) * 2;
        sts1(d, pack_bf(1.f + rbf(untag_sum(v[1].x, v[3].x)), 1.f + rbf(untag_sum(v[1].y, v[3].y))));
        sts1(d + 16, pack_bf(1.f + rbf(untag_sum(v[1].z, v[3].z)), 1.f + rbf(untag_sum(v[1].w, v[3].w))));
        sts1(d + 8, pack_bf(untag_sum(v[0].x, v[2].x), untag_sum(v[0].y, v[2].y)));
        sts1(d + 24, pack_bf(untag_sum(v[0].z, v[2].z), untag_sum(v[0].w, v[2].w)));
        if (wg == 0) {
          uint32_t n = 0;
          while (((s0.x ^ tag) | (s0.y ^ tag)) & 3u) { s0 = ld_relaxed2(g_ln1 + (rb * 128 + tid) * 4); watchdog(n); }
          uint32_t ih, il;
          split_inv(bf_hi(s0.y), ih, il);
          sts4(stage + 4096 + tid * 16, make_uint4(__byte_perm(s0.x, 0, 0x3232), ih, il, 0));
        }
        mbar_arrive(bar_mod);
      }
      cluster_wait();
      if (wg == 1) bar_arrive(2, 256);
      mbar_wait(bar_mod, 0);
      PROF(1, tid == 0, 2);
    }

    float f0 = 0.f, f1 = 0.f;
    const uint32_t rempty = lane < 2 ? mapa(bempty, lane & 1) : 0;
    constexpr uint32_t GE = NSLOT * 8 + 32;
    float o[64], s[64];
#pragma unroll 1
    for (int ps = 0; ps < 3; ps++) {
      {
        const uint32_t xt = ps == 1 ? XT1 : XT2, wt = ps == 1 ? WT1 : WT2;
        const int nst = ps == 2 ? 28 : 14;
        if (ps == 0) {
          float ga[64], gb[64];
#pragma unroll
          for (int i = 0; i < 64; i++) { ga[i] = 0.f; gb[i] = 0.f; }
          uint32_t a[2][16];
          const uint32_t l = fresh_lane();
          const uint4 r0 = lds4(stage + 4096 + (warp * 16 + (l >> 2)) * 16), r1 = lds4(stage + 4096 + 128 + (warp * 16 + (l >> 2)) * 16);
          auto transform = [&](int i, uint32_t (&f)[16], uint32_t z) {
            const uint32_t ad = base + (i & 3) * GST_BYTES + wg * 8192 + frag_offset(warp) + z;
            mbar_wait(xfull + (i & 3) * 8, i >> 2);
#pragma unroll
            for (int kk = 0; kk < 4; kk++) ldmatrix4(ad ^ (kk * 32), f[4 * kk], f[4 * kk + 1], f[4 * kk + 2], f[4 * kk + 3]);
#pragma unroll
            for (int kk = 0; kk < 4; kk++) {
              const uint4 m = lds4(stage + (l & 3) * 16 + ((2 * cj + i) & 15) * 256 + kk * 64);
              f[4 * kk] = ln_mod(f[4 * kk], r0.x, r0.y, r0.z, m.x, m.z);
              f[4 * kk + 1] = ln_mod(f[4 * kk + 1], r1.x, r1.y, r1.z, m.x, m.z);
              f[4 * kk + 2] = ln_mod(f[4 * kk + 2], r0.x, r0.y, r0.z, m.y, m.w);
              f[4 * kk + 3] = ln_mod(f[4 * kk + 3], r1.x, r1.y, r1.z, m.y, m.w);
            }
            keep(f);
            mbar_arrive_pred(xempty + (i & 3) * 8, l == 0);
          };
          auto publish = [&](int u, uint32_t (&f)[16]) {
            const uint32_t sc = stage + 8192 + wg * 8192;
#pragma unroll
            for (int kk = 0; kk < 4; kk++) stmatrix4((sc + frag_offset(warp)) ^ (kk * 32), f[4 * kk], f[4 * kk + 1], f[4 * kk + 2], f[4 * kk + 3]);
            __syncwarp();
            const uint32_t src = sc + (warp & 3) * 2048 + l * 16;
            uint8_t* dst = g_act + (uint32_t)(rb * 80 + cj * 2 + u) * UNIT + warp * 2048 + l * 16;
#pragma unroll
            for (int p4 = 0; p4 < 4; p4++) stg4(dst + p4 * 512, lds4(src + p4 * 512));
            __syncwarp();
            if (u == 1) mbar_arrive_pred(bar_hpub, l == 0);
          };
          auto multiply = [&](int i, uint32_t (&f)[16]) {
            mbar_wait(gfull + (i & 3) * 8, i >> 2);
            const uint64_t db = make_desc(base + (i & 3) * GST_BYTES + UNIT, 8192, 1024);
            wg_fence();
#pragma unroll
            for (int kk = 0; kk < 4; kk++) mma256_rs(ga, gb, f[4 * kk], f[4 * kk + 1], f[4 * kk + 2], f[4 * kk + 3], db + kk * 128);
            wg_commit();
          };
          transform(0, a[0], 0); publish(0, a[0]); transform(1, a[1], 0); multiply(0, a[0]); publish(1, a[1]);
#pragma unroll
          for (int i = 1; i < NRS; i++) {
            if (i >= 2) {
              uint32_t z = r0.w;
#pragma unroll
              for (int k = 0; k < 16; k += 2) asm volatile("lop3.b32 %0, %1, %2, %0, 0xA8;" : "+r"(z) : "r"(a[i & 1][k]), "r"(a[i & 1][k + 1]));
              transform(i, a[i & 1], z);
            }
            multiply(i, a[i & 1]);
            wg_wait<1>();
            mbar_arrive_cl(rempty, GE + ((i + 3) & 3) * 8);
          }
          mbar_arrive_pred(bar_pread, l == 0);
#pragma unroll 1
          for (int i = NRS; i < 14; i++) {
            mbar_wait(xfull + (i & 3) * 8, (i >> 2) & 1);
            mbar_wait(gfull + (i & 3) * 8, (i >> 2) & 1);
            const uint32_t xa = base + (i & 3) * GST_BYTES;
            const uint64_t da = make_desc(xa + wg * 8192, 16, 1024), db = make_desc(xa + UNIT, 8192, 1024);
            if (i == 13) bar_sync(2 + wg, 256);
            wg_fence();
#pragma unroll
            for (int kk = 0; kk < 4; kk++) mma256_ss(ga, gb, da + kk * 2, db + kk * 128, 1);
            wg_commit();
            if (i == 13) bar_arrive(3 - wg, 256);
            wg_wait<1>();
            uint32_t z = r0.w;
#pragma unroll
            for (int k = 0; k < 16; k += 2) asm volatile("lop3.b32 %0, %1, %2, %0, 0xA8;" : "+r"(z) : "r"(a[1][k]), "r"(a[1][k + 1]));
            mbar_arrive_cl(rempty, GE + ((i + 3) & 3) * 8 + z);
            mbar_arrive_pred(xempty + ((i + 3) & 3) * 8, l == 0 && i != NRS);
          }
          mbar_wait(xfull + 16, 1);
          mbar_wait(xfull + 24, 1);
          wg_wait<0>();
          keep(ga); keep(gb);
#pragma unroll
          for (int i = 0; i < 64; i++) {
            asm volatile("mov.b32 %0, %1;" : "=f"(s[i]) : "f"(ga[i]));
            asm volatile("mov.b32 %0, %1;" : "=f"(o[i]) : "f"(gb[i]));
          }
        } else {
          float ga[64], gb[64];
#pragma unroll
          for (int i = 0; i < 64; i++) {
            asm volatile("mov.b32 %0, %1;" : "=f"(ga[i]) : "f"(s[i]));
            asm volatile("mov.b32 %0, %1;" : "=f"(gb[i]) : "f"(o[i]));
          }
#pragma unroll 1
          for (int i = 0; i < nst; i++) {
            mbar_wait(gfull + (i & 3) * 8, (i >> 2) & 1);
            const uint64_t da = make_desc(base + unit_of(xt, i & 3) + wg * 8192, 16, 1024), db = make_desc(base + unit_of(wt, i & 3), 8192, 1024);
            if (i == nst - 1) bar_sync(2 + wg, 256);
            wg_fence();
#pragma unroll
            for (int kk = 0; kk < 4; kk++) mma256_ss(ga, gb, da + kk * 2, db + kk * 128, kk ? 1 : i);
            wg_commit();
            if (i == nst - 1) bar_arrive(3 - wg, 256);
            wg_wait<1>();
            mbar_arrive_cl(rempty, GE + ((i + 3) & 3) * 8, i != 0);
            PROF(4, tid == 0 && (i & 3) == 0, 40 + (ps - 1) * 4 + i / 4);
          }
          wg_wait<0>();
          keep(ga); keep(gb);
#pragma unroll
          for (int i = 0; i < 64; i++) {
            asm volatile("mov.b32 %0, %1;" : "=f"(s[i]) : "f"(ga[i]));
            asm volatile("mov.b32 %0, %1;" : "=f"(o[i]) : "f"(gb[i]));
          }
        }
        mbar_arrive_cl(rempty, GE + (ps == 2 ? 24 : 8));
        if (ps == 2) break;
      }
      const uint32_t qw = base + wg * 8192, qt = QT >> (16 * ps), at = ps ? AT1 : AT0;
      {
        const uint32_t wt = ps ? WT1 : WT0;
        const uint64_t da0 = make_desc(qw + unit_of(qt, 2), 16, 1024), da1 = make_desc(qw + unit_of(qt, 3), 16, 1024);
        const uint64_t db0 = make_desc(base + unit_of(wt, 2), 8192, 1024), db1 = make_desc(base + unit_of(wt, 3), 8192, 1024);
        mbar_wait(gfull + 16, 1);
        mbar_wait(gfull + 24, 1);
        bar_sync(2 + wg, 256);
        wg_fence();
#pragma unroll
        for (int kk = 0; kk < 8; kk++) mma_ss<1>(s, (kk < 4 ? da0 : da1) + (kk & 3) * 2, (kk < 4 ? db0 : db1) + (kk & 3) * 128, 1);
        wg_commit();
        bar_arrive(3 - wg, 256);
        mbar_wait(ps == 0 ? bar_pread : bar_ofree + 8, 0);
        mbar_wait(bfull, 0);
        wg_wait<0>();
        keep(s);
        PROF(2, tid == 0, 8 + ps * 8);
        store_chunk<0>(s, qw + unit_of(qt, 0) + frag_offset(warp));
        store_chunk<1>(s, qw + unit_of(qt, 1) + frag_offset(warp));
        fence_async_smem();
        bar_sync(2 + wg, 256);
        wg_fence();
        issue_qk(s, qw + unit_of(qt, 0), qw + unit_of(qt, 1), base + unit_of(at, 0));
        wg_commit();
#pragma unroll
        for (int kk = 0; kk < 8; kk++) mma_ss<1>(o, (kk < 4 ? da0 : da1) + (kk & 3) * 2, (kk < 4 ? db0 : db1) + UNIT / 16 + (kk & 3) * 128, 1);
        wg_commit();
        bar_arrive(3 - wg, 256);
        wg_wait<1>();
        keep(s);
        mbar_arrive_cl(rempty, 0);
      }
      PROF(4, tid == 0 && ps == 1, 61);
      float l0 = 0.25f, l1 = 0.25f;
      auto step = [&](auto odd_c, const int j, uint32_t (&pw)[32], uint32_t (&pr)[32]) {
        constexpr bool ODD = decltype(odd_c)::value;
        const bool first = !ODD && (j & 2) == 0, last = ODD && j == 7;
        const uint32_t ph = (j >> 1) & 1;
        float i0, i1, a0, a1;
        if (first) { i0 = inv_quad_sum(l0); i1 = inv_quad_sum(l1); l0 = 0.f; l1 = 0.f; }
        bool redo = !ODD && (j | ps) == 0, again = false;
        while (true) {
          if (redo) {
            float m0 = fmaxf(s[0], s[1]), m1 = fmaxf(s[2], s[3]);
#pragma unroll
            for (int i = 1; i < 16; i++) { m0 = fmaxf(m0, fmaxf(s[4 * i], s[4 * i + 1])); m1 = fmaxf(m1, fmaxf(s[4 * i + 2], s[4 * i + 3])); }
            m0 = fmaxf(m0, __shfl_xor_sync(0xffffffffu, m0, 1)); m1 = fmaxf(m1, __shfl_xor_sync(0xffffffffu, m1, 1));
            m0 = fmaxf(m0, __shfl_xor_sync(0xffffffffu, m0, 2)); m1 = fmaxf(m1, __shfl_xor_sync(0xffffffffu, m1, 2));
            m0 *= SCL2; m1 *= SCL2;
            if (!first) {
              m0 = fmaxf(m0, f0); m1 = fmaxf(m1, f1);
              const float c0 = ex2(f0 - m0), c1 = ex2(f1 - m1);
              l0 *= c0; l1 *= c1;
              wg_wait<0>();
              keep(o);
#pragma unroll
              for (int i = 0; i < 16; i++) { o[4 * i] *= c0; o[4 * i + 1] *= c0; o[4 * i + 2] *= c1; o[4 * i + 3] *= c1; }
            }
            f0 = m0; f1 = m1;
          }
          float b0 = 0.f, b1 = 0.f;
          a0 = 0.f; a1 = 0.f;
#pragma unroll
          for (int i = 0; i < 16; i++) {
            const float e0 = ex2(fmaf(s[4 * i], SCL2, -f0)), e1 = ex2(fmaf(s[4 * i + 1], SCL2, -f0));
            const float e2 = ex2(fmaf(s[4 * i + 2], SCL2, -f1)), e3 = ex2(fmaf(s[4 * i + 3], SCL2, -f1));
            a0 += e0; b0 += e1; a1 += e2; b1 += e3;
            pw[2 * i] = pack_bf(e0, e1); pw[2 * i + 1] = pack_bf(e2, e3);
            if (i == VREL) {
#pragma unroll
              for (int k = 0; k < 2 * VREL + 2; k++) asm volatile("" : "+r"(pw[k])::"memory");
              mbar_wait(bfull + (ODD ? 24 : 8), ph);
              wg_wait<0>();
              mbar_arrive_cl(rempty, ODD ? 16 : (j ? 0 : GE + 16), !again);
              if (!ODD) mbar_arrive_cl(rempty, GE + 24, !again && j == 0);
#pragma unroll
              for (int k = 4 * VREL + 4; k < 64; k++) asm volatile("" : "+f"(s[k])::"memory");
            }
          }
          a0 += b0; a1 += b1;
          if (redo) break;
          redo = __any_sync(0xffffffffu, !(a0 + a1 < 0x1p70f));
          if (first) {
            uint32_t m0 = __ballot_sync(0xffffffffu, a0 > 0x1p-50f), m1 = __ballot_sync(0xffffffffu, a1 > 0x1p-50f);
            m0 |= m0 >> 1; m1 |= m1 >> 1; m0 |= m0 >> 2; m1 |= m1 >> 2;
            redo = redo || (m0 & m1 & 0x11111111u) != 0x11111111u;
          }
          if (!redo) break;
          again = true;
        }
        l0 += a0; l1 += a1;
        keep(pw);
        keep(o);
        const uint32_t qo = qt >> (j ? 0 : 8);
        if (first) store_chunk<0>(o, i0, i1, qw + unit_of(qo, 0) + frag_offset(warp));
        keep(o);
        bar_sync(2 + wg, 256);
        if (!last) {
          const uint32_t qn = qt >> (j >= 3 ? 8 : 0);
          wg_fence();
          issue_qk(s, qw + unit_of(qn, 0), qw + unit_of(qn, 1), base + unit_of(at, ODD ? 3 : 1));
          wg_commit();
          mbar_wait(bfull + (ODD ? 0 : 16), ODD ? ph ^ 1 : ph);
        }
        if (first) { store_chunk<1>(o, i0, i1, qw + unit_of(qo, 1) + frag_offset(warp)); keep(o); }
        wg_fence();
        issue_pv(o, pw, base + unit_of(at, ODD ? (last ? 3 : 0) : 2), !first);
        wg_commit();
        bar_arrive(3 - wg, 256);
        if (first) { fence_async_smem(); mbar_arrive_pred(bar_ofull + wg * 8, j); PROF(2, tid == 0 && j, 9 + ps * 8); }
        wg_wait<1>();
        keep(s);
        mbar_arrive_cl(rempty, ODD ? 24 : 8, !last);
        PROF(4, tid == 0 && ps == 1, 51 + j);
      };
      uint32_t pa[32], pb[32];
#pragma unroll 1
      for (int j = 0; j < 8; j += 2) {
        step(std::false_type{}, j, pa, pb);
        step(std::true_type{}, j + 1, pb, pa);
      }
      {
        const float i0 = inv_quad_sum(l0), i1 = inv_quad_sum(l1);
        wg_wait<0>();
        keep(o);
        mbar_arrive_cl(rempty, 24);
        store_chunk<0>(o, i0, i1, qw + unit_of(qt, 2) + frag_offset(warp));
        store_chunk<1>(o, i0, i1, qw + unit_of(qt, 3) + frag_offset(warp));
        fence_async_smem();
        mbar_arrive(bar_ofull + wg * 8);
      }
      PROF(2, tid == 0, 10 + ps * 8);
    }

    const int ln = fresh_lane(), g = ln >> 2, tq = ln & 3, ct = warp * 32 + ln;
    const bool lane0 = ln == 0;
    const int lrow0 = warp * 16 + g;
    const int grow0 = rb * 128 + lrow0;
    const uint32_t res = base + OFF_RES, trow = res + wg * 8192 + frag_offset(warp);
    uint32_t xr[32];
    {
      const uint64_t da = make_desc(base + wg * 8192, 16, 1024), db = make_desc(base, 8192, 1024);
      constexpr int U = UNIT / 16;
      constexpr int XU[4] = {6, 9, 12, 13}, WU[4] = {7, 10, 0, 2};
#define HALF_STAGE(acc, st, hf) _Pragma("unroll") for (int kk = 0; kk < 4; kk++) mma_ss<1>(acc, da + XU[st] * U + kk * 2, db + (WU[st] + hf) * U + kk * 128, 1)
      PROF(10, ct == 0, 19);
      mbar_wait(gfull, 1);
      mbar_wait(gfull + 8, 1);
      wg_fence();
      HALF_STAGE(o, 0, 1);
      HALF_STAGE(o, 1, 1);
      bar_sync(8 + wg, 160);
      HALF_STAGE(o, 2, 1);
      HALF_STAGE(s, 0, 0);
      bar_sync(10 + wg, 160);
      HALF_STAGE(o, 3, 1);
      wg_commit();
      HALF_STAGE(s, 1, 0);
      HALF_STAGE(s, 2, 0);
      wg_commit();
      wg_wait<1>();
      keep(o);
      mbar_arrive_pred(bar_ring0, lane0);
      PROF(8, ct == 0, 20);
      mbar_wait(bar_par, 0);
      uint32_t* xo = g_xch + ((size_t)b * 8 * 256 + ct) * 4;
      const uint32_t par1 = (~lds1(par + PAR_CONST + 48) & 1) << 16;
      uint32_t w[32];
      pack_p(o, w);
#pragma unroll
      for (int i = 0; i < 8; i++) w[4 * i] = (w[4 * i] & ~0x10000u) | par1;
      keep(w);
#pragma unroll
      for (int i = 0; i < 8; i++) st_b128(xo + i * 1024, w[4 * i], w[4 * i + 1], w[4 * i + 2], w[4 * i + 3]);
      wg_fence();
      HALF_STAGE(s, 3, 0);
      wg_commit();
      PROF(8, ct == 0, 21);
      const uint32_t* xi = g_xch + ((size_t)(b ^ 2) * 8 * 256 + ct) * 4;
      uint4 v[8];
      v[XF] = ld_b128(xi + XF * 1024);
      wg_wait<0>();
      keep(s);
      cluster_arrive();
      PROF(10, ct == 0, 23);
      uint32_t n = 0;
      while ((v[XF].x & 0x10000u) != par1) { v[XF] = ld_b128(xi + XF * 1024); watchdog(n); }
      PROF(8, ct == 0, 22);
      mbar_arrive_pred(bar_ring, lane0);
#pragma unroll
      for (int i = 0; i < 8; i++) if (i != XF) v[i] = ld_b128(xi + i * 1024);
      bool ok;
      do {
        ok = true;
#pragma unroll
        for (int i = 0; i < 8; i++)
          if (i != XF && (v[i].x & 0x10000u) != par1) { v[i] = ld_b128(xi + i * 1024); ok = false; }
        watchdog(n);
      } while (!ok);
#pragma unroll
      for (int i = 0; i < 8; i++) {
        s[8 * i] += bf_lo(v[i].x); s[8 * i + 1] += __uint_as_float(v[i].x & 0xfffe0000u); s[8 * i + 2] += bf_lo(v[i].y); s[8 * i + 3] += bf_hi(v[i].y);
        s[8 * i + 4] += bf_lo(v[i].z); s[8 * i + 5] += bf_hi(v[i].z); s[8 * i + 6] += bf_lo(v[i].w); s[8 * i + 7] += bf_hi(v[i].w);
      }
    }
    PROF(8, ct == 0, 28);
    mbar_wait(bar_xres, 0);
    float su0 = 0.f, su1 = 0.f, sq0 = 0.f, sq1 = 0.f, dt0 = 0.f, dt1 = 0.f;
#pragma unroll
    for (int i = 0; i < 16; i++) {
      if (!(i & 1)) {
        ldmatrix4((trow ^ ((i & 7) << 4)) + (i >> 3) * 16384, xr[2 * i], xr[2 * i + 1], xr[2 * i + 2], xr[2 * i + 3]);
      }
      const uint32_t ga = lds1(par + PAR_GA + (8 * i + 2 * tq) * 2);
      const uint2 av = lds2(par + PAR_A + (8 * i + 2 * tq) * 4);
      const uint32_t u0 = hadd2(xr[2 * i], hmul2(ga, pack_bf(s[4 * i], s[4 * i + 1])));
      const uint32_t u1 = hadd2(xr[2 * i + 1], hmul2(ga, pack_bf(s[4 * i + 2], s[4 * i + 3])));
      xr[2 * i] = u0; xr[2 * i + 1] = u1;
      const float a = bf_lo(u0), c = bf_hi(u0), d = bf_lo(u1), e = bf_hi(u1);
      su0 += a + c; su1 += d + e;
      sq0 += a * a + c * c; sq1 += d * d + e * e;
      dt0 += a * __uint_as_float(av.x) + c * __uint_as_float(av.y);
      dt1 += d * __uint_as_float(av.x) + e * __uint_as_float(av.y);
    }
#pragma unroll
    for (int o2 = 1; o2 < 4; o2 <<= 1) {
      su0 += __shfl_xor_sync(0xffffffffu, su0, o2); su1 += __shfl_xor_sync(0xffffffffu, su1, o2);
      sq0 += __shfl_xor_sync(0xffffffffu, sq0, o2); sq1 += __shfl_xor_sync(0xffffffffu, sq1, o2);
      dt0 += __shfl_xor_sync(0xffffffffu, dt0, o2); dt1 += __shfl_xor_sync(0xffffffffu, dt1, o2);
    }
    if (tq < 2) st_b128(g_stats + ((size_t)cj * SEQ + grow0 + tq * 8) * 4, __float_as_uint(tq ? su1 : su0), __float_as_uint(tq ? sq1 : sq0), __float_as_uint(tq ? dt1 : dt0), tag);
    PROF(8, ct == 0, 29);
#pragma unroll
    for (int i = 0; i < 16; i += 2) stmatrix4((trow ^ ((i & 7) << 4)) + (i >> 3) * 16384, xr[2 * i], xr[2 * i + 1], xr[2 * i + 2], xr[2 * i + 3]);
    {
      const uint32_t* sp = g_stats + ((size_t)(2 * tq) * SEQ + grow0) * 4;
      uint4 v0 = ld_b128(sp), v1 = ld_b128(sp + SEQ * 4), v2 = ld_b128(sp + 32), v3 = ld_b128(sp + SEQ * 4 + 32);
      uint32_t n = 0;
      while (v0.w != tag || v1.w != tag || v2.w != tag || v3.w != tag) {
        if (v0.w != tag) v0 = ld_b128(sp);
        if (v1.w != tag) v1 = ld_b128(sp + SEQ * 4);
        if (v2.w != tag) v2 = ld_b128(sp + 32);
        if (v3.w != tag) v3 = ld_b128(sp + SEQ * 4 + 32);
        watchdog(n);
      }
      su0 = __uint_as_float(v0.x) + __uint_as_float(v1.x); sq0 = __uint_as_float(v0.y) + __uint_as_float(v1.y); dt0 = __uint_as_float(v0.z) + __uint_as_float(v1.z);
      su1 = __uint_as_float(v2.x) + __uint_as_float(v3.x); sq1 = __uint_as_float(v2.y) + __uint_as_float(v3.y); dt1 = __uint_as_float(v2.z) + __uint_as_float(v3.z);
    }
#pragma unroll
    for (int o2 = 1; o2 < 4; o2 <<= 1) {
      su0 += __shfl_xor_sync(0xffffffffu, su0, o2); su1 += __shfl_xor_sync(0xffffffffu, su1, o2);
      sq0 += __shfl_xor_sync(0xffffffffu, sq0, o2); sq1 += __shfl_xor_sync(0xffffffffu, sq1, o2);
      dt0 += __shfl_xor_sync(0xffffffffu, dt0, o2); dt1 += __shfl_xor_sync(0xffffffffu, dt1, o2);
    }
    PROF(8, ct == 0, 30);
    float mb0, sd0, mb1, sd1;
    {
      const float m0 = su0 * (1.f / DM), m1 = su1 * (1.f / DM);
      ln_scalars(m0, fmaxf(sq0 * (1.f / DM) - m0 * m0, 0.f), mb0, sd0);
      ln_scalars(m1, fmaxf(sq1 * (1.f / DM) - m1 * m1, 0.f), mb1, sd1);
    }
    const float inv0 = 1.f / sd0, inv1 = 1.f / sd1;
    uint32_t ih0, il0, ih1, il1;
    split_inv(sd0, ih0, il0);
    split_inv(sd1, ih1, il1);
    const uint4 cst = lds4(par + PAR_CONST);
    const float A1 = __uint_as_float(cst.x) + __uint_as_float(cst.z), A2 = __uint_as_float(cst.y) + __uint_as_float(cst.w);
    const float r0 = (dt0 - mb0 * A1) * inv0 + A2, r1 = (dt1 - mb1 * A1) * inv1 + A2;
    float rbest = r1 > r0 ? r1 : r0;
    int ibest = r1 > r0 ? lrow0 + 8 : lrow0;
#pragma unroll
    for (int o2 = 4; o2 < 32; o2 <<= 1) {
      const float ro = __shfl_xor_sync(0xffffffffu, rbest, o2);
      const int io = __shfl_xor_sync(0xffffffffu, ibest, o2);
      if (ro > rbest || (ro == rbest && io < ibest)) { rbest = ro; ibest = io; }
    }
    if (lane0) sts2(par + PAR_RED + warp * 8, __float_as_uint(rbest), ibest);
    PROF(8, ct == 0, 38);
    mbar_wait(bar_rst, 0);
    bar_sync(1, 256);
    PROF(8, ct == 0, 39);
    {
      const uint2 cv = lds2(par + PAR_RED + (ln & 7) * 8);
      rbest = __uint_as_float(cv.x); ibest = cv.y;
#pragma unroll
      for (int o2 = 1; o2 < 8; o2 <<= 1) {
        const float ro = __shfl_xor_sync(0xffffffffu, rbest, o2);
        const int io = __shfl_xor_sync(0xffffffffu, ibest, o2);
        if (ro > rbest || (ro == rbest && io < ibest)) { rbest = ro; ibest = io; }
      }
    }
    if (cj == 0 && ct == 0) st_relaxed2(g_cand + rb * 8, tagf(rbest, tag), ((rb * 128 + ibest) << 2) | tag);
    const uint32_t mm0 = pack_bf(mb0, mb0), mm1 = pack_bf(mb1, mb1);
    if ((ibest >> 4) == warp) {
      const bool hi = ibest & 8;
      const int src = (ibest & 7) * 4, ch = g * 2;
      const uint32_t mm = __shfl_sync(0xffffffffu, hi ? mm1 : mm0, src), ih = __shfl_sync(0xffffffffu, hi ? ih1 : ih0, src), il = __shfl_sync(0xffffffffu, hi ? il1 : il0, src);
      const uint32_t xa = res + (ch >> 3) * 16384 + ibest * 128 + (((ch & 7) ^ (ibest & 7)) << 4) + tq * 4;
      const uint32_t x0 = lds1(xa), x1 = lds1(xa ^ 16);
      const uint32_t pc = par + (8 * ch + 2 * tq) * 2;
      const uint32_t h0 = ln_mod(x0, mm, ih, il, lds1(pc + PAR_CB1), lds1(pc + PAR_SB)), h1 = ln_mod(x1, mm, ih, il, lds1(pc + PAR_CB1 + 16), lds1(pc + PAR_SB + 16));
      uint32_t* dst = g_row + rb * 2 * DM + cj * 128 + ln * 4;
      st_pairs(dst, h0, h1, tag);
      st_pairs(dst + DM, x0, x1, tag);
      __syncwarp();
    }
    uint32_t wf[128];
    const uint32_t frow = (ln & 7) + (ln >> 4) * 8;
    const uint32_t wfa = base + OFF_GATE + warp * 8192 + frow * 64 + ((((ln >> 3) & 1) ^ ((frow >> 1) & 3)) << 4);
#define LOAD_WF(f) ldmatrix4t((wfa ^ (((f) & 1) * 32)) + (((f) >> 1) & 1) * 4 * UNIT + ((f) >> 2) * 1024, wf[4 * (f)], wf[4 * (f) + 1], wf[4 * (f) + 2], wf[4 * (f) + 3])
    const bool early = __all_sync(0xffffffffu, b >= NFFN || mbar_test(bar_w1, 0));
    PROF(8, ct == 0, 37);
#pragma unroll
    for (int i = 0; i < 16; i += 2) {
      uint32_t ov[4];
      if (early) {
#pragma unroll
        for (int mt = 0; mt < 4; mt++) LOAD_WF(i * 2 + mt);
      }
#pragma unroll
      for (int u = 0; u < 2; u++) {
        const int ii = i + u;
        const uint32_t cb1 = lds1(par + PAR_CB1 + (8 * ii + 2 * tq) * 2), sb = lds1(par + PAR_SB + (8 * ii + 2 * tq) * 2);
        const uint32_t gb = lds1(par + PAR_GB + (8 * ii + 2 * tq) * 2);
        const uint32_t h0 = ln_mod(xr[2 * ii], mm0, ih0, il0, cb1, sb), h1 = ln_mod(xr[2 * ii + 1], mm1, ih1, il1, cb1, sb);
        ov[2 * u] = hadd2(xr[2 * ii], hmul2(gb, h0));
        ov[2 * u + 1] = hadd2(xr[2 * ii + 1], hmul2(gb, h1));
      }
      stmatrix4((trow ^ ((i & 7) << 4)) + (i >> 3) * 16384, ov[0], ov[1], ov[2], ov[3]);
    }
    PROF(8, ct == 0, 31);
    auto store_tile = [&](int skip) {
      const int wrow0 = wg * 64 + (warp & 3) * 16;
#pragma unroll
      for (int p = 0; p < 8; p++) {
        const int row = 2 * p + (ln >> 4), ch = ln & 15;
        const uint4 v = lds4(res + (ch >> 3) * 16384 + (wrow0 + row) * 128 + (((ch & 7) ^ (row & 7)) << 4));
        if (rb * 128 + wrow0 + row != skip) *reinterpret_cast<uint4*>(P.out + (size_t)(rb * 128 + wrow0 + row) * DM + cj * 128 + ch * 8) = v;
      }
    };
    uint2 cv = ld_relaxed2(g_cand + (ln & 15) * 8);
    if (!early) {
      mbar_wait(bar_w1, 0);
#pragma unroll
      for (int f = 0; f < 32; f++) LOAD_WF(f);
    }
    float rwin; int iwin;
    uint4 hv[8];
    uint32_t wd[64];
    const uint32_t wda = base + warp * 8192 + frow * 128 + ((((ln >> 3) & 1) ^ (ln & 7)) << 4);
#define LOAD_WD(f) ldmatrix4t((wda ^ ((((f) >> 1) & 3) * 32)) + ((f) >> 3) * 4096 + ((f) & 1) * 2048, wd[4 * (f)], wd[4 * (f) + 1], wd[4 * (f) + 2], wd[4 * (f) + 3])
    {
      uint32_t n = 0;
      int cur = -1;
      while (true) {
        const bool valid = !(((cv.x ^ tag) | (cv.y ^ tag)) & 3u);
        const uint32_t bits = cv.x & ~3u;
        const uint32_t key = valid ? ((int)bits < 0 ? ~bits : bits | 0x80000000u) : 0u;
        const uint32_t best = __reduce_max_sync(0xffffffffu, key);
        const int src = (__ffs(__ballot_sync(0xffffffffu, key == best)) - 1) & 15;
        if (best && src != cur) {
          cur = src;
#pragma unroll
          for (int i = 0; i < 8; i++) hv[i] = ld_pairs(g_row + cur * 2 * DM + warp * 128 + i * 16 + tq * 4);
        }
        if (__all_sync(0xffffffffu, valid)) break;
        if (!valid) cv = ld_relaxed2(g_cand + (ln & 15) * 8);
        watchdog(n);
      }
      rwin = __uint_as_float(__shfl_sync(0xffffffffu, cv.x, cur) & ~3u);
      iwin = __shfl_sync(0xffffffffu, cv.y, cur) >> 2;
    }
    PROF(8, ct == 0, 32);
    const uint32_t* wrow = g_row + (iwin >> 7) * 2 * DM;
    if (b < NFFN) {
      {
        uint32_t n = 0;
        bool ok;
        do {
          ok = true;
#pragma unroll
          for (int i = 0; i < 8; i++)
            if (hv[i].y != tag || hv[i].w != tag) { hv[i] = ld_pairs(wrow + warp * 128 + i * 16 + tq * 4); ok = false; }
          watchdog(n);
        } while (!ok);
      }
      __syncwarp();
      PROF(8, ct == 0, 33);
      float d[8][4];
#pragma unroll
      for (int i = 0; i < 8; i++) { d[i][0] = 0.f; d[i][1] = 0.f; d[i][2] = 0.f; d[i][3] = 0.f; }
#pragma unroll
      for (int ks = 0; ks < 8; ks++) {
#pragma unroll
        for (int mt = 0; mt < 4; mt++) {
          const int r = ks * 16 + mt * 4;
          mma16816(d[mt + (ks & 1) * 4], wf[r], wf[r + 1], wf[r + 2], wf[r + 3], hv[ks].x, hv[ks].z);
        }
        if (ks == 1) mbar_wait(bar_w2, 0);
        if (ks >= 1) {
#pragma unroll
          for (int f = 4 * ks - 4; f < 16 && f < 4 * ks; f++) LOAD_WD(f);
        }
      }
      const uint32_t red = base + OFF_GATE;
      if (tq == 0) {
        const uint32_t dst = red + warp * 8192 + g * 32;
        sts4(dst, make_uint4(__float_as_uint(d[0][0] + d[4][0]), __float_as_uint(d[0][2] + d[4][2]), __float_as_uint(d[1][0] + d[5][0]), __float_as_uint(d[1][2] + d[5][2])));
        sts4(dst + 16, make_uint4(__float_as_uint(d[2][0] + d[6][0]), __float_as_uint(d[2][2] + d[6][2]), __float_as_uint(d[3][0] + d[7][0]), __float_as_uint(d[3][2] + d[7][2])));
      }
      bar_sync(1, 256);
      uint32_t ab[4];
      {
        float G = 0.f, U = 0.f;
        const uint32_t src = red + (ln & 7) * 32 + (ln >> 3) * 4;
#pragma unroll
        for (int w8 = 0; w8 < 8; w8++) { G += __uint_as_float(lds1(src + w8 * 8192)); U += __uint_as_float(lds1(src + w8 * 8192 + 16)); }
        const float act = rbf(silu_f(rbf(G))) * rbf(U);
        const uint32_t pk = pack_bf(act, __shfl_down_sync(0xffffffffu, act, 1));
#pragma unroll
        for (int i = 0; i < 4; i++) ab[i] = __shfl_sync(0xffffffffu, pk, i * 8 + tq * 2);
      }
      PROF(8, ct == 0, 34);
#pragma unroll
      for (int mt = 0; mt < 8; mt++) {
        d[mt][0] = 0.f; d[mt][1] = 0.f; d[mt][2] = 0.f; d[mt][3] = 0.f;
        mma16816(d[mt], wd[mt * 8], wd[mt * 8 + 1], wd[mt * 8 + 2], wd[mt * 8 + 3], ab[0], ab[1]);
        mma16816(d[mt], wd[mt * 8 + 4], wd[mt * 8 + 5], wd[mt * 8 + 6], wd[mt * 8 + 7], ab[2], ab[3]);
      }
#pragma unroll
      for (int i = 0; i < 4; i++) {
        const int m4 = (i >> 1) * 4, e = (i & 1) * 2;
        const float y = (tq & 2) ? ((tq & 1) ? d[m4 + 3][e] : d[m4 + 2][e]) : ((tq & 1) ? d[m4 + 1][e] : d[m4][e]);
        st_relaxed(g_ypart + ((size_t)(warp * 16 + (m4 + tq) * 2 + (i & 1)) * NFFN + b) * 8 + g, tagf(y, tag));
      }
      PROF(8, ct == 0, 35);
    }
    store_tile(iwin);
    {
      uint2 fh = make_uint2(0, 0), fx = make_uint2(0, 0);
      const uint32_t* src = wrow + (b >> 1) * 16 + (ct & 3) * 4 + (b & 1) * 2;
      if (ct < 4) { fh = ld_pair(src); fx = ld_pair(src + DM); }
      float y0 = 0.f, y1 = 0.f, y2 = 0.f, y3 = 0.f;
      if (ct < 2 * NFFN) {
        const uint4 v = poll4(g_ypart + (size_t)b * NFFN * 8 + ct * 4, tag);
        y0 = __uint_as_float(v.x & ~3u); y1 = __uint_as_float(v.y & ~3u); y2 = __uint_as_float(v.z & ~3u); y3 = __uint_as_float(v.w & ~3u);
      }
      __syncwarp();
      PROF(8, ct == 0, 5); PROF(8, ct == 96, 11); PROF(8, ct == 192, 12);
      if (ct < 4) {
        uint32_t n = 0;
        while (fh.y != tag || fx.y != tag) { fh = ld_pair(src); fx = ld_pair(src + DM); watchdog(n); }
      }
#pragma unroll
      for (int o2 = 2; o2 < 32; o2 <<= 1) {
        y0 += __shfl_xor_sync(0xffffffffu, y0, o2); y1 += __shfl_xor_sync(0xffffffffu, y1, o2);
        y2 += __shfl_xor_sync(0xffffffffu, y2, o2); y3 += __shfl_xor_sync(0xffffffffu, y3, o2);
      }
      if (ln < 2) sts4(par + PAR_RED + 64 + warp * 32 + ln * 16, make_uint4(__float_as_uint(y0), __float_as_uint(y1), __float_as_uint(y2), __float_as_uint(y3)));
      PROF(8, ct == 0, 6);
      bar_sync(1, 256);
      PROF(8, ct == 0, 7);
      if (ct < 4) {
        float ya = 0.f, yb = 0.f;
#pragma unroll
        for (int w8 = 0; w8 < 7; w8++) {
          const uint2 v = lds2(par + PAR_RED + 64 + w8 * 32 + ct * 8);
          ya += __uint_as_float(v.x); yb += __uint_as_float(v.y);
        }
        const float rs = rbf(1.f / (1.f + __expf(-rbf(rwin))));
        const uint2 gv = lds2(par + PAR_CONST + 16 + ct * 8);
        const uint32_t upd = hmul2(pack_bf(ya, yb), pack_bf(rs, rs));
        *reinterpret_cast<uint32_t*>(P.out + (size_t)iwin * DM + b * 8 + ct * 2) =
            hadd2(fx.x, hmul2(__byte_perm(gv.x, gv.y, 0x7632), hadd2(fh.x, upd)));
      }
      if (b == 0 && ct == 0) st_relaxed(&g_epoch, lds1(par + PAR_CONST + 48) + 1);
    }
    PROF(15, ct == 0, 36);
    cluster_wait();
  }
}

typedef CUresult (*EncodeFn)(CUtensorMap*, CUtensorMapDataType, cuuint32_t, void*, const cuuint64_t*, const cuuint64_t*,
                             const cuuint32_t*, const cuuint32_t*, CUtensorMapInterleave, CUtensorMapSwizzle,
                             CUtensorMapL2promotion, CUtensorMapFloatOOBfill);

void map2d(EncodeFn enc, CUtensorMap* m, const void* p, uint64_t rows, uint64_t cols, uint32_t brows) {
  cuuint64_t dims[2] = {cols, rows}, strides[1] = {cols * 2};
  cuuint32_t box[2] = {64, brows}, es[2] = {1, 1};
  enc(m, CU_TENSOR_MAP_DATA_TYPE_BFLOAT16, 2, const_cast<void*>(p), dims, strides, box, es, CU_TENSOR_MAP_INTERLEAVE_NONE,
      CU_TENSOR_MAP_SWIZZLE_128B, CU_TENSOR_MAP_L2_PROMOTION_L2_256B, CU_TENSOR_MAP_FLOAT_OOB_FILL_NONE);
}
void map2d_narrow(EncodeFn enc, CUtensorMap* m, const void* p, uint64_t rows, uint64_t cols) {
  cuuint64_t dims[2] = {cols, rows}, strides[1] = {cols * 2};
  cuuint32_t box[2] = {32, 256}, es[2] = {1, 1};
  enc(m, CU_TENSOR_MAP_DATA_TYPE_BFLOAT16, 2, const_cast<void*>(p), dims, strides, box, es, CU_TENSOR_MAP_INTERLEAVE_NONE,
      CU_TENSOR_MAP_SWIZZLE_64B, CU_TENSOR_MAP_L2_PROMOTION_L2_64B, CU_TENSOR_MAP_FLOAT_OOB_FILL_NONE);
}
void map3d(EncodeFn enc, CUtensorMap* m, const void* p, uint64_t rows, uint64_t cols, uint32_t brows, uint32_t nch) {
  cuuint64_t dims[3] = {64, rows, cols / 64}, strides[2] = {cols * 2, 128};
  cuuint32_t box[3] = {64, brows, nch}, es[3] = {1, 1, 1};
  enc(m, CU_TENSOR_MAP_DATA_TYPE_BFLOAT16, 3, const_cast<void*>(p), dims, strides, box, es, CU_TENSOR_MAP_INTERLEAVE_NONE,
      CU_TENSOR_MAP_SWIZZLE_128B, CU_TENSOR_MAP_L2_PROMOTION_L2_256B, CU_TENSOR_MAP_FLOAT_OOB_FILL_NONE);
}

}

extern "C" void kernel_launch(void* const* d_in, const int* in_sizes, int n_in, void* d_out, int out_size) {
  (void)in_sizes; (void)n_in; (void)out_size;
  static EncodeFn enc = nullptr;
  if (!enc) {
    void* fn = nullptr;
    cudaDriverEntryPointQueryResult st;
    cudaGetDriverEntryPoint("cuTensorMapEncodeTiled", &fn, cudaEnableDefault, &st);
    enc = (EncodeFn)fn;
    cudaFuncSetAttribute(fused_kernel, cudaFuncAttributeMaxDynamicSharedMemorySize, SMEM_BYTES);
  }
  Maps maps;
  map2d(enc, &maps.x, d_in[0], SEQ, DM, 128);
  map3d(enc, &maps.wq, d_in[3], DM, NQ, 64, 2);
  map3d(enc, &maps.k, d_in[1], 4 * SK, 128, 128, 1);
  map3d(enc, &maps.v, d_in[2], 4 * SK, 128, 128, 1);
  map3d(enc, &maps.wo, d_in[4], NQ, DM, 64, 2);
  map2d_narrow(enc, &maps.wg, d_in[7], DM, FF);
  map2d_narrow(enc, &maps.wu, d_in[8], DM, FF);
  map3d(enc, &maps.wd, d_in[9], FF, DM, 32, 4);
  map2d_narrow(enc, &maps.wm, d_in[11], DM, NMOD);
  Ptrs p;
  p.x = (const __nv_bfloat16*)d_in[0];
  p.w_r = (const __nv_bfloat16*)d_in[6];
  p.w_gate = (const __nv_bfloat16*)d_in[7];
  p.w_up = (const __nv_bfloat16*)d_in[8];
  p.w_down = (const __nv_bfloat16*)d_in[9];
  p.c = (const __nv_bfloat16*)d_in[10];
  p.w_mod = (const __nv_bfloat16*)d_in[11];
  p.out = (__nv_bfloat16*)d_out;
  fused_kernel<<<NMAIN + NHELP, 384, SMEM_BYTES>>>(maps, p);
}
```

```cpp
#include <cuda_runtime.h>
#include <cuda_bf16.h>
#include <cuda.h>
#include <stdint.h>
#include <type_traits>

#define HD 1
#define HDX 2
#define XF 4
#define XE 32
#define XR 0
#define PF2 1
#define PF2T 1
#define NRS 6
#define FPACE 2
#define GOST 24
#define WB 2
#define WN 16
#define RES0 17
#define RES1 20
#define HU 16
#define VREL 7
#define E0 3

namespace {

constexpr int SEQ = 2048, DM = 1024, NQ = 4096, SK = 2048, WIN = 512, FF = 3584, NMOD = 6144;
constexpr int NMAIN = 128, NHELP = 4, NFFN = 112;
constexpr int NSLOT = 4, SLOT_BYTES = 32768, UNIT = 16384, GST_BYTES = 3 * UNIT;
constexpr uint32_t XT0 = 0x9630, XT1 = 0x54DC, XT2 = 0xDC96;
constexpr uint32_t WT0 = 0xA741, WT1 = 0x720A, WT2 = 0x20A7;
constexpr uint32_t AT0 = 0x7420, AT1 = 0x2C0A;
constexpr uint32_t QT = 0x549696DC;
constexpr int OFF_STAGE = 12 * UNIT;
constexpr uint32_t FT_G = 0xB876, FT_U = 0xA931, FT_D = 0x2D0C;
constexpr int OFF_RES = 4 * UNIT;
constexpr int OFF_PAR = 14 * UNIT;
constexpr int OFF_BAR = OFF_PAR + 2048 + 512;
constexpr int SMEM_BYTES = OFF_BAR + 512;
static_assert(SMEM_BYTES <= 232448, "smem");

constexpr int PAR_T1 = 0;
constexpr int PAR_T2 = 1024;
constexpr int PAR_CONST = 1536;
constexpr int PAR_RED = 1600;
constexpr int PAR_SINK = 2176;

struct Maps {
  CUtensorMap x, wq, k, v, wo, wg, wu, wd, wm;
};
struct Ptrs {
  const __nv_bfloat16 *x, *w_r, *c, *w_mod, *w_gate, *w_up, *w_down;
  __nv_bfloat16* out;
};

__device__ __align__(1024) uint8_t g_act[16 * 80 * UNIT];
__device__ __align__(128) uint32_t g_mod[NMOD];
__device__ __align__(128) uint32_t g_modp[2 * 2 * DM];
__device__ __align__(128) uint32_t g_ln1[SEQ * 4];
__device__ __align__(128) uint32_t g_cnt_h[16 * 32];
__device__ __align__(128) uint32_t g_cnt_o[128 * 32];
__device__ __align__(128) uint32_t g_xch[NMAIN * 8 * 256 * 4];
__device__ __align__(128) uint32_t g_stats[8 * SEQ * 4];
__device__ __align__(128) uint32_t g_cand[NMAIN * 32];
__device__ __align__(128) uint32_t g_row[16 * 2 * DM];
__device__ __align__(128) uint32_t g_ypart[NMAIN * NFFN * 8];
__device__ uint32_t g_epoch;

__device__ __forceinline__ uint32_t fresh_lane() { uint32_t l; asm volatile("mov.u32 %0, %%laneid;" : "=r"(l)); return l; }
__device__ __forceinline__ uint32_t frag_offset(int warp) {
  const uint32_t l = fresh_lane();
  return ((warp & 3) * 16 + (l & 15)) * 128 + (((l >> 4) ^ (l & 7)) << 4);
}
__device__ __forceinline__ bool elect_one() {
  uint32_t p;
  asm volatile("{ .reg .pred q; elect.sync _|q, 0xffffffff; selp.u32 %0, 1, 0, q; }" : "=r"(p));
  return p;
}
__device__ __forceinline__ uint32_t smem_u32(const void* p) { return (uint32_t)__cvta_generic_to_shared(p); }
__device__ __forceinline__ void mbar_init(uint32_t bar, uint32_t cnt) {
  asm volatile("mbarrier.init.shared::cta.b64 [%0], %1;" ::"r"(bar), "r"(cnt) : "memory");
}
__device__ __forceinline__ void mbar_expect_tx(uint32_t bar, uint32_t bytes) {
  asm volatile("mbarrier.arrive.expect_tx.shared::cta.b64 _, [%0], %1;" ::"r"(bar), "r"(bytes) : "memory");
}
__device__ __forceinline__ void mbar_arrive(uint32_t bar) {
  asm volatile("mbarrier.arrive.shared::cta.b64 _, [%0];" ::"r"(bar) : "memory");
}
__device__ __forceinline__ void mbar_arrive_pred(uint32_t bar, bool p) {
  asm volatile("{ .reg .pred p; setp.ne.b32 p, %1, 0; @p mbarrier.arrive.shared::cta.b64 _, [%0]; }" ::"r"(bar), "r"((int)p) : "memory");
}
__device__ __forceinline__ void mbar_arrive_cl(uint32_t bar, uint32_t off, bool p = true) {
  asm volatile("{ .reg .pred p, q; .reg .b32 a; setp.ne.b32 q, %2, 0; setp.ne.and.b32 p, %0, 0, q; add.u32 a, %0, %1; @p mbarrier.arrive.shared::cluster.b64 _, [a]; }"
               ::"r"(bar), "r"(off), "r"((int)p) : "memory");
}
__device__ __forceinline__ uint32_t mapa(uint32_t addr, uint32_t cta) {
  uint32_t r; asm("mapa.shared::cluster.u32 %0, %1, %2;" : "=r"(r) : "r"(addr), "r"(cta)); return r;
}
__device__ __forceinline__ void cluster_arrive() { asm volatile("barrier.cluster.arrive.relaxed.aligned;" ::: "memory"); }
__device__ __forceinline__ void cluster_wait() { asm volatile("barrier.cluster.wait.aligned;" ::: "memory"); }
__device__ __forceinline__ void watchdog(uint32_t& n) {
}
__device__ __forceinline__ void mbar_wait(uint32_t bar, uint32_t parity) {
  asm volatile("{\n.reg .pred p;\nWAIT_%=:\nmbarrier.try_wait.parity.shared::cta.b64 p, [%0], %1;\n@!p bra WAIT_%=;\n}" ::"r"(bar), "r"(parity) : "memory");
}
__device__ __forceinline__ bool mbar_test(uint32_t bar, uint32_t parity) {
  uint32_t ok;
  asm volatile("{\n.reg .pred p;\nmbarrier.test_wait.parity.shared::cta.b64 p, [%1], %2;\nselp.u32 %0, 1, 0, p;\n}" : "=r"(ok) : "r"(bar), "r"(parity) : "memory");
  return ok;
}
__device__ __forceinline__ uint64_t l2_stream() {
  uint64_t f; asm("createpolicy.fractional.L2::evict_first.b64 %0, 1.0;" : "=l"(f)); return f;
}
__device__ __forceinline__ void tma2d(uint32_t dst, const CUtensorMap* m, int c0, int c1, uint32_t bar) {
  asm volatile("cp.async.bulk.tensor.2d.shared::cluster.global.mbarrier::complete_tx::bytes.L2::cache_hint [%0], [%1, {%3, %4}], [%2], %5;"
               ::"r"(dst), "l"(m), "r"(bar), "r"(c0), "r"(c1), "l"(l2_stream()) : "memory");
}
__device__ __forceinline__ void tma3d_prefetch(const CUtensorMap* m, int c0, int c1, int c2) {
  asm volatile("cp.async.bulk.prefetch.tensor.3d.L2.global.tile [%0, {%1, %2, %3}];" ::"l"(m), "r"(c0), "r"(c1), "r"(c2) : "memory");
}
__device__ __forceinline__ void bulk_load(uint32_t dst, const void* src, uint32_t bytes, uint32_t bar) {
  asm volatile("cp.async.bulk.shared::cluster.global.mbarrier::complete_tx::bytes [%0], [%1], %2, [%3];" ::"r"(dst), "l"(src), "r"(bytes), "r"(bar) : "memory");
}
__device__ __forceinline__ void bulk_load_stream(uint32_t dst, const void* src, uint32_t bytes, uint32_t bar) {
  asm volatile("cp.async.bulk.shared::cluster.global.mbarrier::complete_tx::bytes.L2::cache_hint [%0], [%1], %2, [%3], %4;"
               ::"r"(dst), "l"(src), "r"(bytes), "r"(bar), "l"(l2_stream()) : "memory");
}
__device__ __forceinline__ void bulk_store(void* dst, uint32_t src, uint32_t bytes) {
  asm volatile("cp.async.bulk.global.shared::cta.bulk_group [%0], [%1], %2;" ::"l"(dst), "r"(src), "r"(bytes) : "memory");
}
__device__ __forceinline__ uint32_t unit_of(uint32_t table, uint32_t i) { return ((table >> (i * 4)) & 15) * UNIT; }
__device__ __forceinline__ void tma3d(uint32_t dst, const CUtensorMap* m, int c0, int c1, int c2, uint32_t bar) {
  asm volatile("cp.async.bulk.tensor.3d.shared::cluster.global.mbarrier::complete_tx::bytes.L2::cache_hint [%0], [%1, {%3, %4, %5}], [%2], %6;"
               ::"r"(dst), "l"(m), "r"(bar), "r"(c0), "r"(c1), "r"(c2), "l"(l2_stream()) : "memory");
}
template <bool STREAM>
__device__ __forceinline__ void tma3d_mc(uint32_t dst, const CUtensorMap* m, int c0, int c1, int c2, uint32_t bar) {
  if (STREAM)
    asm volatile("cp.async.bulk.tensor.3d.shared::cluster.global.mbarrier::complete_tx::bytes.multicast::cluster.L2::cache_hint [%0], [%1, {%3, %4, %5}], [%2], %6, %7;"
                 ::"r"(dst), "l"(m), "r"(bar), "r"(c0), "r"(c1), "r"(c2), "h"((uint16_t)3), "l"(l2_stream()) : "memory");
  else
    asm volatile("cp.async.bulk.tensor.3d.shared::cluster.global.mbarrier::complete_tx::bytes.multicast::cluster [%0], [%1, {%3, %4, %5}], [%2], %6;"
                 ::"r"(dst), "l"(m), "r"(bar), "r"(c0), "r"(c1), "r"(c2), "h"((uint16_t)3) : "memory");
}
__device__ __forceinline__ void prefetch_map(const CUtensorMap* m) {
  asm volatile("prefetch.tensormap [%0];" ::"l"(m) : "memory");
}
__device__ __forceinline__ void fence_async() { asm volatile("fence.proxy.async.global;" ::: "memory"); }
__device__ __forceinline__ void fence_async_smem() { asm volatile("fence.proxy.async.shared::cta;" ::: "memory"); }
__device__ __forceinline__ void bar_sync(int id, int n) { asm volatile("bar.sync %0, %1;" ::"r"(id), "r"(n) : "memory"); }
__device__ __forceinline__ void bar_arrive(int id, int n) { asm volatile("bar.arrive %0, %1;" ::"r"(id), "r"(n) : "memory"); }
__device__ __forceinline__ void wg_fence() { asm volatile("wgmma.fence.sync.aligned;" ::: "memory"); }
__device__ __forceinline__ void wg_commit() { asm volatile("wgmma.commit_group.sync.aligned;" ::: "memory"); }
template <int N> __device__ __forceinline__ void wg_wait() { asm volatile("wgmma.wait_group.sync.aligned %0;" ::"n"(N) : "memory"); }
__device__ __forceinline__ uint64_t make_desc(uint32_t addr, uint32_t lbo, uint32_t sbo) {
  return (uint64_t)((addr & 0x3FFFF) >> 4) | ((uint64_t)(lbo >> 4) << 16) | ((uint64_t)(sbo >> 4) << 32) | (1ull << 62);
}
__device__ __forceinline__ uint32_t ld_relaxed(const uint32_t* p) {
  uint32_t v; asm volatile("ld.relaxed.gpu.global.u32 %0, [%1];" : "=r"(v) : "l"(p) : "memory"); return v;
}
__device__ __forceinline__ uint32_t ld_acquire(const uint32_t* p) {
  uint32_t v; asm volatile("ld.acquire.gpu.global.u32 %0, [%1];" : "=r"(v) : "l"(p) : "memory"); return v;
}
__device__ __forceinline__ uint4 ld_relaxed4(const uint32_t* p) {
  uint4 v; asm volatile("ld.relaxed.gpu.global.v4.u32 {%0,%1,%2,%3}, [%4];" : "=r"(v.x), "=r"(v.y), "=r"(v.z), "=r"(v.w) : "l"(p) : "memory"); return v;
}
__device__ __forceinline__ uint2 ld_relaxed2(const uint32_t* p) {
  uint2 v; asm volatile("ld.relaxed.gpu.global.v2.u32 {%0,%1}, [%2];" : "=r"(v.x), "=r"(v.y) : "l"(p) : "memory"); return v;
}
__device__ __forceinline__ void st_relaxed(uint32_t* p, uint32_t v) {
  asm volatile("st.relaxed.gpu.global.u32 [%0], %1;" ::"l"(p), "r"(v) : "memory");
}
__device__ __forceinline__ void st_relaxed2(uint32_t* p, uint32_t a, uint32_t b) {
  asm volatile("st.relaxed.gpu.global.v2.u32 [%0], {%1,%2};" ::"l"(p), "r"(a), "r"(b) : "memory");
}
__device__ __forceinline__ void st_relaxed4(uint32_t* p, uint32_t a, uint32_t b, uint32_t c, uint32_t d) {
  asm volatile("st.relaxed.gpu.global.v4.u32 [%0], {%1,%2,%3,%4};" ::"l"(p), "r"(a), "r"(b), "r"(c), "r"(d) : "memory");
}
__device__ __forceinline__ void st_b128(uint32_t* p, uint32_t a, uint32_t b, uint32_t c, uint32_t d) {
  asm volatile("{ .reg .b64 u, v; .reg .b128 w; mov.b64 u, {%1, %2}; mov.b64 v, {%3, %4}; mov.b128 w, {u, v}; st.relaxed.gpu.global.b128 [%0], w; }"
               ::"l"(p), "r"(a), "r"(b), "r"(c), "r"(d) : "memory");
}
__device__ __forceinline__ uint4 ld_b128(const uint32_t* p) {
  uint4 r;
  asm volatile("{ .reg .b64 u, v; .reg .b128 w; ld.relaxed.gpu.global.b128 w, [%4]; mov.b128 {u, v}, w; mov.b64 {%0, %1}, u; mov.b64 {%2, %3}, v; }"
               : "=r"(r.x), "=r"(r.y), "=r"(r.z), "=r"(r.w) : "l"(p) : "memory");
  return r;
}
__device__ __forceinline__ void st_pairs(uint32_t* p, uint32_t a, uint32_t b, uint32_t tag) {
  asm volatile("{ .reg .b64 u, v; mov.b64 u, {%1, %3}; mov.b64 v, {%2, %3}; st.relaxed.gpu.global.v2.b64 [%0], {u, v}; }"
               ::"l"(p), "r"(a), "r"(b), "r"(tag) : "memory");
}
__device__ __forceinline__ uint4 ld_pairs(const uint32_t* p) {
  uint4 v;
  asm volatile("{ .reg .b64 u, v; ld.relaxed.gpu.global.v2.b64 {u, v}, [%4]; mov.b64 {%0, %1}, u; mov.b64 {%2, %3}, v; }"
               : "=r"(v.x), "=r"(v.y), "=r"(v.z), "=r"(v.w) : "l"(p) : "memory");
  return v;
}
__device__ __forceinline__ uint2 ld_pair(const uint32_t* p) {
  uint2 v;
  asm volatile("{ .reg .b64 u; ld.relaxed.gpu.global.b64 u, [%2]; mov.b64 {%0, %1}, u; }" : "=r"(v.x), "=r"(v.y) : "l"(p) : "memory");
  return v;
}
__device__ __forceinline__ void red_release(uint32_t* p, uint32_t v) {
  asm volatile("red.release.gpu.global.add.u32 [%0], %1;" ::"l"(p), "r"(v) : "memory");
}
__device__ __forceinline__ uint32_t ldg_nc1(const void* p) {
  uint32_t v;
  asm volatile("ld.global.nc.u32 %0, [%1];" : "=r"(v) : "l"(p));
  return v;
}
__device__ __forceinline__ uint4 ldg_nc4(const void* p) {
  uint4 v; asm volatile("ld.global.nc.L1::no_allocate.v4.u32 {%0,%1,%2,%3}, [%4];" : "=r"(v.x), "=r"(v.y), "=r"(v.z), "=r"(v.w) : "l"(p)); return v;
}
__device__ __forceinline__ void stg4(void* p, uint4 v) {
  asm volatile("st.global.v4.u32 [%0], {%1,%2,%3,%4};" ::"l"(p), "r"(v.x), "r"(v.y), "r"(v.z), "r"(v.w) : "memory");
}
__device__ __forceinline__ void wait_counter(const uint32_t* p, uint32_t target) {
  uint32_t n = 0;
  while ((int)(ld_acquire(p) - target) < 0) { watchdog(n); }
}
__device__ __forceinline__ uint32_t tagf(float v, uint32_t tag) { return (__float_as_uint(v) & ~3u) | tag; }
__device__ __forceinline__ bool tag_ok(uint4 v, uint32_t tag) { return (((v.x ^ tag) | (v.y ^ tag) | (v.z ^ tag) | (v.w ^ tag)) & 3u) == 0; }
__device__ __forceinline__ float untag_sum(uint32_t a, uint32_t b) { return __uint_as_float(a & ~3u) + __uint_as_float(b & ~3u); }
__device__ __forceinline__ uint4 poll4(const uint32_t* p, uint32_t tag) {
  uint4 v = ld_relaxed4(p);
  uint32_t n = 0;
  while (!tag_ok(v, tag)) { v = ld_relaxed4(p); watchdog(n); }
  return v;
}
__device__ __forceinline__ float bf_lo(uint32_t v) { return __uint_as_float(v << 16); }
__device__ __forceinline__ float bf_hi(uint32_t v) { return __uint_as_float(v & 0xffff0000u); }
__device__ __forceinline__ uint32_t pack_bf(float lo, float hi) {
  uint32_t r; asm("cvt.rn.bf16x2.f32 %0, %1, %2;" : "=r"(r) : "f"(hi), "f"(lo)); return r;
}
__device__ __forceinline__ float rbf(float v) { return __uint_as_float(pack_bf(0.f, v) & 0xffff0000u); }
__device__ __forceinline__ uint32_t hmul2(uint32_t a, uint32_t b) {
  uint32_t r; asm("mul.rn.bf16x2 %0, %1, %2;" : "=r"(r) : "r"(a), "r"(b)); return r;
}
__device__ __forceinline__ uint32_t hadd2(uint32_t a, uint32_t b) {
  uint32_t r; asm("add.rn.bf16x2 %0, %1, %2;" : "=r"(r) : "r"(a), "r"(b)); return r;
}
__device__ __forceinline__ uint32_t hsub2(uint32_t a, uint32_t b) {
  uint32_t r; asm("sub.rn.bf16x2 %0, %1, %2;" : "=r"(r) : "r"(a), "r"(b)); return r;
}
__device__ __forceinline__ uint32_t hmax2(uint32_t a, uint32_t b) {
  uint32_t r; asm("max.bf16x2 %0, %1, %2;" : "=r"(r) : "r"(a), "r"(b)); return r;
}
__device__ __forceinline__ float ex2(float x) { float r; asm("ex2.approx.ftz.f32 %0, %1;" : "=f"(r) : "f"(x)); return r; }
__device__ __forceinline__ void stmatrix4(uint32_t addr, uint32_t a, uint32_t b, uint32_t c, uint32_t d) {
  asm volatile("stmatrix.sync.aligned.m8n8.x4.shared.b16 [%0], {%1,%2,%3,%4};" ::"r"(addr), "r"(a), "r"(b), "r"(c), "r"(d) : "memory");
}
__device__ __forceinline__ void ldmatrix4(uint32_t addr, uint32_t& a, uint32_t& b, uint32_t& c, uint32_t& d) {
  asm volatile("ldmatrix.sync.aligned.m8n8.x4.shared.b16 {%0,%1,%2,%3}, [%4];" : "=r"(a), "=r"(b), "=r"(c), "=r"(d) : "r"(addr) : "memory");
}
__device__ __forceinline__ void ldmatrix4t(uint32_t addr, uint32_t& a, uint32_t& b, uint32_t& c, uint32_t& d) {
  asm volatile("ldmatrix.sync.aligned.m8n8.x4.trans.shared.b16 {%0,%1,%2,%3}, [%4];" : "=r"(a), "=r"(b), "=r"(c), "=r"(d) : "r"(addr) : "memory");
}
__device__ __forceinline__ void mma16816(float (&d)[4], uint32_t a0, uint32_t a1, uint32_t a2, uint32_t a3, uint32_t b0, uint32_t b1) {
  asm volatile("mma.sync.aligned.m16n8k16.row.col.f32.bf16.bf16.f32 {%0,%1,%2,%3}, {%4,%5,%6,%7}, {%8,%9}, {%0,%1,%2,%3};"
               : "+f"(d[0]), "+f"(d[1]), "+f"(d[2]), "+f"(d[3]) : "r"(a0), "r"(a1), "r"(a2), "r"(a3), "r"(b0), "r"(b1));
}
__device__ __forceinline__ void sts1(uint32_t a, uint32_t v) { asm volatile("st.shared.u32 [%0], %1;" ::"r"(a), "r"(v) : "memory"); }
__device__ __forceinline__ uint4 lds4(uint32_t a) {
  uint4 v; asm volatile("ld.shared.v4.u32 {%0,%1,%2,%3}, [%4];" : "=r"(v.x), "=r"(v.y), "=r"(v.z), "=r"(v.w) : "r"(a) : "memory"); return v;
}
__device__ __forceinline__ uint2 lds2(uint32_t a) {
  uint2 v; asm volatile("ld.shared.v2.u32 {%0,%1}, [%2];" : "=r"(v.x), "=r"(v.y) : "r"(a) : "memory"); return v;
}
__device__ __forceinline__ uint32_t lds1(uint32_t a) {
  uint32_t v; asm volatile("ld.shared.u32 %0, [%1];" : "=r"(v) : "r"(a) : "memory"); return v;
}
__device__ __forceinline__ void sts2(uint32_t a, uint32_t x, uint32_t y) { asm volatile("st.shared.v2.u32 [%0], {%1,%2};" ::"r"(a), "r"(x), "r"(y) : "memory"); }
__device__ __forceinline__ void sts4(uint32_t a, uint4 v) {
  asm volatile("st.shared.v4.u32 [%0], {%1,%2,%3,%4};" ::"r"(a), "r"(v.x), "r"(v.y), "r"(v.z), "r"(v.w) : "memory");
}
__device__ __forceinline__ float silu_f(float v) { return __fdividef(v, 1.f + __expf(-v)); }
__device__ __forceinline__ uint32_t hfma2(uint32_t a, uint32_t b, uint32_t c) {
  uint32_t r; asm("fma.rn.bf16x2 %0, %1, %2, %3;" : "=r"(r) : "r"(a), "r"(b), "r"(c)); return r;
}
__device__ __forceinline__ void split_inv(float sd, uint32_t& ih, uint32_t& il) {
  const float inv = 1.f / sd;
  ih = pack_bf(inv, inv);
  const float lo = inv - bf_lo(ih);
  il = pack_bf(lo, lo);
}
__device__ __forceinline__ uint32_t ln_mod(uint32_t x, uint32_t mean2, uint32_t ih, uint32_t il, uint32_t c1, uint32_t sh) {
  const uint32_t d = hsub2(x, mean2);
  return hadd2(hmul2(hfma2(d, ih, hmul2(d, il)), c1), sh);
}

#define R8(a, i) "+f"(a[i]), "+f"(a[i + 1]), "+f"(a[i + 2]), "+f"(a[i + 3]), "+f"(a[i + 4]), "+f"(a[i + 5]), "+f"(a[i + 6]), "+f"(a[i + 7])
#define D64 "{%0,%1,%2,%3,%4,%5,%6,%7,%8,%9,%10,%11,%12,%13,%14,%15,%16,%17,%18,%19,%20,%21,%22,%23,%24,%25,%26,%27,%28,%29,%30,%31," \
            "%32,%33,%34,%35,%36,%37,%38,%39,%40,%41,%42,%43,%44,%45,%46,%47,%48,%49,%50,%51,%52,%53,%54,%55,%56,%57,%58,%59,%60,%61,%62,%63}"
template <int TB>
__device__ __forceinline__ void mma_ss(float (&d)[64], uint64_t da, uint64_t db, int sc) {
  asm volatile("{\n.reg .pred p;\nsetp.ne.b32 p, %66, 0;\n"
               "wgmma.mma_async.sync.aligned.m64n128k16.f32.bf16.bf16 " D64 ", %64, %65, p, 1, 1, 0, %67;\n}"
               : R8(d, 0), R8(d, 8), R8(d, 16), R8(d, 24), R8(d, 32), R8(d, 40), R8(d, 48), R8(d, 56)
               : "l"(da), "l"(db), "r"(sc), "n"(TB));
}
template <int TB>
__device__ __forceinline__ void mma_rs(float (&d)[64], uint32_t a0, uint32_t a1, uint32_t a2, uint32_t a3, uint64_t db, int sc) {
  asm volatile("{\n.reg .pred p;\nsetp.ne.b32 p, %69, 0;\n"
               "wgmma.mma_async.sync.aligned.m64n128k16.f32.bf16.bf16 " D64 ", {%64,%65,%66,%67}, %68, p, 1, 1, %70;\n}"
               : R8(d, 0), R8(d, 8), R8(d, 16), R8(d, 24), R8(d, 32), R8(d, 40), R8(d, 48), R8(d, 56)
               : "r"(a0), "r"(a1), "r"(a2), "r"(a3), "l"(db), "r"(sc), "n"(TB));
}
#define D128 "{%0,%1,%2,%3,%4,%5,%6,%7,%8,%9,%10,%11,%12,%13,%14,%15,%16,%17,%18,%19,%20,%21,%22,%23,%24,%25,%26,%27,%28,%29,%30,%31," \
             "%32,%33,%34,%35,%36,%37,%38,%39,%40,%41,%42,%43,%44,%45,%46,%47,%48,%49,%50,%51,%52,%53,%54,%55,%56,%57,%58,%59,%60,%61,%62,%63," \
             "%64,%65,%66,%67,%68,%69,%70,%71,%72,%73,%74,%75,%76,%77,%78,%79,%80,%81,%82,%83,%84,%85,%86,%87,%88,%89,%90,%91,%92,%93,%94,%95," \
             "%96,%97,%98,%99,%100,%101,%102,%103,%104,%105,%106,%107,%108,%109,%110,%111,%112,%113,%114,%115,%116,%117,%118,%119,%120,%121,%122,%123,%124,%125,%126,%127}"
#define R128(d, e) R8(d, 0), R8(d, 8), R8(d, 16), R8(d, 24), R8(d, 32), R8(d, 40), R8(d, 48), R8(d, 56), \
                   R8(e, 0), R8(e, 8), R8(e, 16), R8(e, 24), R8(e, 32), R8(e, 40), R8(e, 48), R8(e, 56)
__device__ __forceinline__ void mma256_ss(float (&d)[64], float (&e)[64], uint64_t da, uint64_t db, int sc) {
  asm volatile("{\n.reg .pred p;\nsetp.ne.b32 p, %130, 0;\n"
               "wgmma.mma_async.sync.aligned.m64n256k16.f32.bf16.bf16 " D128 ", %128, %129, p, 1, 1, 0, 1;\n}"
               : R128(d, e) : "l"(da), "l"(db), "r"(sc));
}
__device__ __forceinline__ void mma256_rs(float (&d)[64], float (&e)[64], uint32_t a0, uint32_t a1, uint32_t a2, uint32_t a3, uint64_t db) {
  asm volatile("{\n.reg .pred p;\nsetp.ne.b32 p, 1, 0;\n"
               "wgmma.mma_async.sync.aligned.m64n256k16.f32.bf16.bf16 " D128 ", {%128,%129,%130,%131}, %132, p, 1, 1, 1;\n}"
               : R128(d, e) : "r"(a0), "r"(a1), "r"(a2), "r"(a3), "l"(db));
}
template <int N> __device__ __forceinline__ void keep(float (&a)[N]) {
#pragma unroll
  for (int i = 0; i < N; i++) asm volatile("" : "+f"(a[i])::"memory");
}
template <int N> __device__ __forceinline__ void keep(uint32_t (&a)[N]) {
#pragma unroll
  for (int i = 0; i < N; i++) asm volatile("" : "+r"(a[i])::"memory");
}

#define PROF(grp, cond, idx) do {} while (0)

constexpr float SCL2 = 1.4426950408889634f * 0.08838834764831845f;

__device__ __forceinline__ void pack_p(const float (&s)[64], uint32_t (&p)[32]) {
#pragma unroll
  for (int i = 0; i < 32; i++) p[i] = pack_bf(s[2 * i], s[2 * i + 1]);
}

__device__ __forceinline__ void issue_qk(float (&s)[64], uint32_t q0, uint32_t q1, uint32_t kslot) {
  const uint64_t db = make_desc(kslot, 16, 1024), da0 = make_desc(q0, 16, 1024), da1 = make_desc(q1, 16, 1024);
#pragma unroll
  for (int kk = 0; kk < 8; kk++) mma_ss<0>(s, (kk < 4 ? da0 : da1) + (kk & 3) * 2, db + (kk >> 2) * 1024 + (kk & 3) * 2, kk != 0);
}
__device__ __forceinline__ void issue_pv(float (&o)[64], uint32_t (&p)[32], uint32_t vslot, int acc) {
  uint64_t db = make_desc(vslot, 16384, 1024);
#pragma unroll
  for (int kk = 0; kk < 8; kk++)
    mma_rs<1>(o, p[4 * kk], p[4 * kk + 1], p[4 * kk + 2], p[4 * kk + 3], db + kk * 128, kk == 0 ? acc : 1);
}

template <int H>
__device__ __forceinline__ void store_chunk(const float (&a)[64], uint32_t addr) {
#pragma unroll
  for (int i = 8 * H; i < 8 * H + 8; i += 2)
    stmatrix4(addr ^ ((i & 7) << 4), pack_bf(a[4 * i], a[4 * i + 1]), pack_bf(a[4 * i + 2], a[4 * i + 3]),
              pack_bf(a[4 * i + 4], a[4 * i + 5]), pack_bf(a[4 * i + 6], a[4 * i + 7]));
}
template <int H>
__device__ __forceinline__ void store_chunk(const float (&a)[64], float i0, float i1, uint32_t addr) {
#pragma unroll
  for (int i = 8 * H; i < 8 * H + 8; i += 2)
    stmatrix4(addr ^ ((i & 7) << 4), pack_bf(a[4 * i] * i0, a[4 * i + 1] * i0), pack_bf(a[4 * i + 2] * i1, a[4 * i + 3] * i1),
              pack_bf(a[4 * i + 4] * i0, a[4 * i + 5] * i0), pack_bf(a[4 * i + 6] * i1, a[4 * i + 7] * i1));
}
__device__ __forceinline__ float inv_quad_sum(float l) {
  l += __shfl_xor_sync(0xffffffffu, l, 1);
  l += __shfl_xor_sync(0xffffffffu, l, 2);
  return __fdividef(1.f, l);
}

__device__ __forceinline__ void ln_scalars(float mean, float var, float& mb, float& sd) {
  mb = rbf(mean);
  sd = rbf(sqrtf(rbf(rbf(var) + 1e-5f)));
}

__global__ void __cluster_dims__(2, 1, 1) __launch_bounds__(384, 1) fused_kernel(const __grid_constant__ Maps maps, const Ptrs P) {
  extern __shared__ __align__(1024) uint8_t smem_raw[];
  const uint32_t base = smem_u32(smem_raw);
  const int tid = threadIdx.x, lane = tid & 31;
  const int warp = __shfl_sync(0xffffffffu, tid >> 5, 0);
  const int b = blockIdx.x;
  PROF(15, tid == 0, 0);

  if (b >= NMAIN) {
    float* sc = reinterpret_cast<float*>(smem_raw);
    float* red = sc + DM;
    for (int k = tid; k < DM; k += 384) sc[k] = rbf(silu_f(__bfloat162float(P.c[k])));
    __syncthreads();
    if (tid < 256) {
      const int col = 2048 + (b - NMAIN) * 1024 + (tid & 127) * 8, r0 = (tid >> 7) * 512;
      float acc[8];
#pragma unroll
      for (int e = 0; e < 8; e++) acc[e] = 0.f;
#pragma unroll 1
      for (int r = r0; r < r0 + 512; r += HU) {
        uint4 w[HU];
#pragma unroll
        for (int u = 0; u < HU; u++) w[u] = ldg_nc4(P.w_mod + (size_t)(r + u) * NMOD + col);
#pragma unroll
        for (int u = 0; u < HU; u++) {
          float s = sc[r + u];
          acc[0] += s * bf_lo(w[u].x); acc[1] += s * bf_hi(w[u].x); acc[2] += s * bf_lo(w[u].y); acc[3] += s * bf_hi(w[u].y);
          acc[4] += s * bf_lo(w[u].z); acc[5] += s * bf_hi(w[u].z); acc[6] += s * bf_lo(w[u].w); acc[7] += s * bf_hi(w[u].w);
        }
      }
      if (tid >= 128) {
#pragma unroll
        for (int e = 0; e < 8; e++) red[(tid & 127) * 8 + e] = acc[e];
      }
      const uint32_t tag = ld_relaxed(&g_epoch) % 3 + 1;
      bar_sync(1, 256);
      if (tid < 128) {
        uint32_t o[8];
#pragma unroll
        for (int e = 0; e < 8; e++) o[e] = __float_as_uint(rbf(acc[e] + red[tid * 8 + e])) | tag;
        st_relaxed4(g_mod + col, o[0], o[1], o[2], o[3]);
        st_relaxed4(g_mod + col + 4, o[4], o[5], o[6], o[7]);
      }
    }
    PROF(2, tid == 0, 1);
    return;
  }

  const int rank = b & 1;
  const int rb = ((b >> 4) << 1) | rank, cj = (b >> 1) & 7;
  const uint32_t bfull = base + OFF_BAR, bempty = bfull + NSLOT * 8;
  const uint32_t gfull = bempty + NSLOT * 8, gempty = gfull + 32;
  const uint32_t bar_ofull = gempty + 32;
  const uint32_t bar_ofree = bar_ofull + 16;
  const uint32_t bar_par = bar_ofree + 32;
  const uint32_t bar_mod = bar_par + 8;
  const uint32_t bar_pread = bar_mod + 8;
  const uint32_t bar_xres = bar_pread + 8;
  const uint32_t bar_ring = bar_xres + 8;
  const uint32_t bar_box = bar_ring + 24;
  const uint32_t bar_go = bar_box + 96;
  const uint32_t bar_go2 = bar_go + 16;
  const uint32_t bar_cnt = bar_go + 24;
  const uint32_t xfull = bar_go + 32, xempty = xfull + 32;
  const uint32_t bar_hw = xempty + 32, bar_hx = bar_hw + 8;
  const uint32_t bar_hpub = bar_hx + 16;
  const uint32_t bar_res = bar_go + 8;
  const uint32_t stage = base + OFF_STAGE, par = base + OFF_PAR;

  if (warp == 8 && elect_one()) {
    for (int s = 0; s < NSLOT; s++) { mbar_init(bfull + s * 8, 1); mbar_init(bempty + s * 8, 16); }
    for (int s = 0; s < 4; s++) { mbar_init(gfull + s * 8, 1); mbar_init(gempty + s * 8, 16); mbar_init(xfull + s * 8, 1); mbar_init(xempty + s * 8, 8); mbar_init(bar_ofree + s * 8, 1); }
    mbar_init(bar_ofull, 128); mbar_init(bar_ofull + 8, 128);
    mbar_init(bar_par, 64); mbar_init(bar_mod, 256); mbar_init(bar_pread, 8); mbar_init(bar_xres, 1);
    mbar_init(bar_ring, 8); mbar_init(bar_ring + 8, 8); mbar_init(bar_ring + 16, 8);
    mbar_init(bar_go, 1); mbar_init(bar_go2, 1); mbar_init(bar_cnt, 1); mbar_init(bar_hpub, 8); mbar_init(bar_res, 1);
    for (int s = 0; s < 12; s++) mbar_init(bar_box + s * 8, 1);
    asm volatile("fence.mbarrier_init.release.cluster;" ::: "memory");
    prefetch_map(&maps.x); prefetch_map(&maps.wq); prefetch_map(&maps.k); prefetch_map(&maps.v);
  }
  if (warp == 9 && elect_one()) {
    mbar_init(bar_hw, 1); mbar_init(bar_hx, 1); mbar_init(bar_hx + 8, 1);
    asm volatile("fence.mbarrier_init.release.cluster;" ::: "memory");
    mbar_expect_tx(bar_hw, 32768);
    mbar_expect_tx(bar_hx, 16384);
    mbar_expect_tx(bar_hx + 8, 16384);
    const __nv_bfloat16* xs = P.x + (size_t)(rb * 128 + cj * 16) * DM;
    bulk_load(base + 2 * GST_BYTES, xs, 16384, bar_hx);
    tma2d(stage, &maps.wm, (b >> 1) * 32, rank * 512, bar_hw);
    tma2d(stage + 16384, &maps.wm, (b >> 1) * 32, rank * 512 + 256, bar_hw);
    bulk_load(base + 3 * GST_BYTES, xs + 8 * DM, 16384, bar_hx + 8);
  }
  cluster_arrive();

  if (warp >= 8) {
    asm volatile("setmaxnreg.dec.sync.aligned.u32 40;");
    if (warp < 10) bar_arrive(1, 320);
    cluster_wait();
    if (warp == 8) {
      const int kvrow = (cj >> 1) * SK + (SK - WIN);
      int wch = cj * 8 + rank * 2;
#pragma unroll 1
      for (int ps = 0; ps < 3; ps++) {
        const CUtensorMap* mw = ps == 2 ? &maps.wo : &maps.wq;
        const uint32_t xt = ps == 1 ? XT1 : XT2, wt = ps == 0 ? WT0 : (ps == 1 ? WT1 : WT2);
        const int nst = ps == 2 ? 32 : 16;
        if (ps) {
          mbar_wait(bar_ofree + (ps - 1) * 16, 0);
          fence_async();
        }
#pragma unroll 1
        for (int i = 0; i < nst; i++) {
          const uint32_t bf = gfull + (i & 3) * 8;
          const int kt = ps == 2 ? (((cj & 1) * 4 + ((i >> 1) & 3)) * 4 + (i >> 3)) * 2 + (i & 1) : (i + (ps ? 0 : b & 14)) & 15;
          const uint32_t wd = base + unit_of(wt, i & 3) + rank * UNIT, xd = base + unit_of(xt, i & 3);
          const uint8_t* xs = g_act + (uint32_t)(rb * 80 + (ps - 1) * 16 + kt) * UNIT;
          if (ps == 0 && i == HD) mbar_wait(bar_mod, 0);
          if (ps && i && i < 4) mbar_wait(bempty + (i == 3 ? 3 : i - 1) * 8, 1);
          mbar_wait(gempty + (i & 3) * 8, ((i >> 2) & 1) ^ 1);
          if (elect_one()) {
            mbar_expect_tx(bf, ps ? GST_BYTES : 2 * UNIT);
            tma3d_mc<true>(wd, mw, 0, kt * 64, wch, bf);
          }
          if (ps) {
            if (i == 16) mbar_wait(bar_cnt, 0);
            if (i == 2) mbar_wait(bempty + 16, 1);
            if (elect_one()) {
              bulk_load_stream(xd, xs, UNIT, bf);
              mbar_arrive_pred(ps == 1 ? bar_go2 : bar_go, i == (ps == 1 ? 15 : GOST - 1));
              mbar_arrive_pred(bar_res, ((1u << RES0 | 1u << RES1) >> i) & 1);
            }
          }
        }
        if (ps == 2) break;
        wch = ps ? ((wch >> 3) ^ rank) * 2 : wch + 4;
#pragma unroll 1
        for (int u = 0; u < 16; u++) {
          const bool isk = (u == 0) || ((u & 1) && u < 15);
          const int blk = (isk ? (u + 1) >> 1 : (u == 15 ? 7 : (u >> 1) - 1)) & 3;
          const uint32_t sl = base + unit_of(ps ? AT1 : AT0, u & 3) + rank * UNIT, bf = bfull + (u & 3) * 8;
          if (u < 4) mbar_wait(gempty + ((u + 1) >> 1) * 8, 1);
          mbar_wait(bempty + (u & 3) * 8, ((u >> 2) & 1) ^ 1);
          if (elect_one()) {
            mbar_expect_tx(bf, SLOT_BYTES);
            tma3d_mc<false>(sl, isk ? &maps.k : &maps.v, 0, kvrow + blk * 128, rank, bf);
          }
        }
      }
      if (b < NFFN) {
#pragma unroll 1
        for (int u = 0; u < 12; u++) {
          if (u == 0 || u == 3 || u == 6) mbar_wait(bar_ring + (u / 3) * 8, 0);
          if (u >= FPACE) mbar_wait(bar_box + (u - FPACE) * 8, 0);
          const uint32_t dst = base + unit_of(u < 4 ? FT_G : (u < 8 ? FT_U : FT_D), u & 3);
          if (elect_one()) {
            mbar_expect_tx(bar_box + u * 8, UNIT);
            if (u < 8) tma2d(dst, u < 4 ? &maps.wg : &maps.wu, b * 32, (u & 3) * 256, bar_box + u * 8);
            else tma3d(dst, &maps.wd, 0, b * 32, (u - 8) * 4, bar_box + u * 8);
          }
        }
      }
    } else if (warp == 9) {
      const uint32_t target = 8 * (ld_relaxed(&g_epoch) + 1);
#pragma unroll 1
      for (int i = 0; i < 16; i++) {
        if (i == HDX) mbar_wait(bar_mod, 0);
        if (i == NRS) {
          wait_counter(&g_cnt_h[rb * 32], target);
          PROF(1, lane == 0, 26);
          fence_async();
        }
        mbar_wait(xempty + (i & 3) * 8, ((i >> 2) & 1) ^ 1);
        if (elect_one()) {
          mbar_expect_tx(xfull + (i & 3) * 8, UNIT);
          if (i < NRS) tma2d(base + (i & 3) * GST_BYTES, &maps.x, ((2 * cj + i) & 15) * 64, rb * 128, xfull + (i & 3) * 8);
          else bulk_load_stream(base + (i & 3) * GST_BYTES, g_act + (uint32_t)(rb * 80 + ((2 * cj + i) & 15)) * UNIT, UNIT, xfull + (i & 3) * 8);
        }
      }
      prefetch_map(&maps.wo);
#pragma unroll 1
      for (int t = 0; t < 4; t++) {
#pragma unroll 1
        for (int w = 0; w < 2; w++) {
          mbar_wait(bar_ofull + w * 8, t & 1);
          uint8_t* dst = g_act + (uint32_t)(rb * 80 + 16 + (cj * 4 + t) * 2) * UNIT + w * 8192;
          if (elect_one()) {
            bulk_store(dst, base + unit_of(QT, 2 * t) + w * 8192, 8192);
            bulk_store(dst + UNIT, base + unit_of(QT, 2 * t + 1) + w * 8192, 8192);
            asm volatile("cp.async.bulk.commit_group;" ::: "memory");
          }
        }
        if (elect_one()) {
          asm volatile("cp.async.bulk.wait_group.read 0;" ::: "memory");
          mbar_arrive(bar_ofree + t * 8);
          asm volatile("cp.async.bulk.wait_group 0;" ::: "memory");
          fence_async();
          red_release(&g_cnt_o[((rb * 4 + t) * 2 + (cj >> 2)) * 32], 2);
          if (t == PF2T) for (int u = 0; u < PF2; u++)
            tma3d_prefetch(&maps.wo, 0, ((((cj & 1) * 4 + (b >> 5)) * 4 + u) * 2 + ((b >> 4) & 1)) * 64, (cj ^ rank) * 2);
        }
        if (t & 1) {
          wait_counter(&g_cnt_o[(rb * 8 + 2 * t - 2 + (cj & 1)) * 32], target);
          wait_counter(&g_cnt_o[(rb * 8 + 2 * t + (cj & 1)) * 32], target);
        }
      }
      fence_async();
      if (elect_one()) {
        mbar_arrive(bar_cnt);
        PROF(2, true, 27);
        mbar_expect_tx(bar_xres, 32768);
      }
#pragma unroll 1
      for (int u = 0; u < 2; u++) {
        mbar_wait(bar_res, u);
        if (elect_one()) tma2d(base + OFF_RES + u * UNIT, &maps.x, cj * 128 + u * 64, rb * 128, bar_xres);
      }
    } else {
      const int t2 = tid - 320;
      if (t2 == 0) {
        mbar_wait(bar_hpub, 0);
        PROF(1, true, 24);
        red_release(&g_cnt_h[rb * 32], 1);
        PROF(1, true, 25);
        prefetch_map(&maps.wg); prefetch_map(&maps.wu); prefetch_map(&maps.wd);
      }
      __syncwarp();
      if (b < NFFN) {
        mbar_wait(bar_go2, 0);
        const __nv_bfloat16* pg = ((b & 1) ? P.w_up : P.w_gate) + (b >> 1) * 64 + (size_t)t2 * FF;
        const __nv_bfloat16* pd = P.w_down + (size_t)b * 32768 + t2 * 64;
        PROF(2, t2 == 0, 13);
#pragma unroll 1
        for (int i = 0; i < WN; i += WB) {
          uint32_t v[WB];
#pragma unroll
          for (int u = 0; u < WB; u++)
            asm volatile("ld.global.cg.L2::128B.u32 %0, [%1];" : "=r"(v[u]) : "l"(i < 16 ? pg + (size_t)(i + u) * 64 * FF : pd + (i + u - 16) * 4096));
#pragma unroll
          for (int u = 1; u < WB; u++) v[0] ^= v[u];
          sts1(par + PAR_SINK + t2 * 4, v[0]);
        }
        PROF(2, t2 == 0, 14);
      }
      const uint32_t epoch = ld_relaxed(&g_epoch), tag = epoch % 3 + 1;
      mbar_wait(bar_xres, 0);
      float s1 = 0.f, s2 = 0.f;
#pragma unroll 1
      for (int q = 0; q < 4; q++) {
        const int col = q * 256 + t2 * 4;
        uint4 vsb = poll4(g_mod + 3 * DM + col, tag), vcb = poll4(g_mod + 4 * DM + col, tag);
        uint2 wr = *reinterpret_cast<const uint2*>(P.w_r + col);
        float c0 = rbf(1.f + bf_hi(vcb.x)), c1 = rbf(1.f + bf_hi(vcb.y)), c2 = rbf(1.f + bf_hi(vcb.z)), c3 = rbf(1.f + bf_hi(vcb.w));
        float a0 = c0 * bf_lo(wr.x), a1 = c1 * bf_hi(wr.x), a2 = c2 * bf_lo(wr.y), a3 = c3 * bf_hi(wr.y);
        s1 += (a0 + a1) + (a2 + a3);
        s2 += bf_hi(vsb.x) * bf_lo(wr.x) + bf_hi(vsb.y) * bf_hi(wr.x) + bf_hi(vsb.z) * bf_lo(wr.y) + bf_hi(vsb.w) * bf_hi(wr.y);
        if ((col >> 7) == cj) {
          const int lc = col & 127;
          uint4 vga = poll4(g_mod + 2 * DM + col, tag), vgb = poll4(g_mod + 5 * DM + col, tag);
          sts4(par + PAR_T1 + lc * 8, make_uint4(__byte_perm(vga.x, vga.y, 0x7632), __byte_perm(vgb.x, vgb.y, 0x7632), __float_as_uint(a0), __float_as_uint(a1)));
          sts4(par + PAR_T1 + lc * 8 + 16, make_uint4(__byte_perm(vga.z, vga.w, 0x7632), __byte_perm(vgb.z, vgb.w, 0x7632), __float_as_uint(a2), __float_as_uint(a3)));
          sts4(par + PAR_T2 + lc * 4, make_uint4(pack_bf(c0, c1), __byte_perm(vsb.x, vsb.y, 0x7632), pack_bf(c2, c3), __byte_perm(vsb.z, vsb.w, 0x7632)));
        }
      }
#pragma unroll
      for (int o = 16; o > 0; o >>= 1) { s1 += __shfl_xor_sync(0xffffffffu, s1, o); s2 += __shfl_xor_sync(0xffffffffu, s2, o); }
      if (lane == 0) { sts2(par + PAR_CONST + (warp - 10) * 8, __float_as_uint(s1), __float_as_uint(s2)); sts1(par + PAR_CONST + 48, epoch); }
      if (t2 < 2) {
        uint4 g = poll4(g_mod + 5 * DM + b * 8 + t2 * 4, tag);
        sts4(par + PAR_CONST + 16 + t2 * 16, g);
      }
      mbar_wait(bar_go, 0);
#pragma unroll 4
      for (int q = XR; q < XE; q++) st_b128(g_xch + ((size_t)b * 8 * 256 + q * 64 + t2) * 4, (epoch & 1) << 16, 0, 0, 0);
      for (int q = 0; q < 2; q++) st_relaxed4(g_stats + ((size_t)cj * SEQ + rb * 128 + q * 64 + t2) * 4, 0, 0, 0, 0);
      if (b < NFFN)
        for (int q = 0; q < 4; q++) st_relaxed4(g_ypart + ((size_t)(q * 32 + (t2 >> 1)) * NFFN + b) * 8 + (t2 & 1) * 4, 0, 0, 0, 0);
      st_relaxed4(g_row + rb * 2 * DM + (t2 >> 5) * DM + cj * 128 + (t2 & 31) * 4, 0, 0, 0, 0);
      if (t2 < 16) st_relaxed2(g_cand + (cj * 16 + t2) * 32 + rb * 2, 0, 0);
      __threadfence();
      mbar_arrive(bar_par);
    }
    __syncwarp();
    cluster_arrive();
    cluster_wait();
  } else {
    const int wg = warp >> 2;

    uint32_t tag;
    {
      uint32_t* const pmod = g_modp + rank * 2 * DM + (b >> 1) * 32 + lane;
      uint32_t* const pln = g_ln1 + (rb * 128 + cj * 16 + warp) * 4;
      const uint32_t cv = ldg_nc1(P.c + rank * 512 + tid * 2);
      const uint32_t epoch = ld_relaxed(&g_epoch);
      if (warp == 0) st_relaxed(pmod, 0);
      if (lane == 0) { st_relaxed2(pln, 0, 0); st_relaxed2(pln + 32, 0, 0); }
      asm volatile("setmaxnreg.inc.sync.aligned.u32 232;");
      sts1(par + tid * 4, pack_bf(silu_f(bf_lo(cv)), silu_f(bf_hi(cv))));
      bar_sync(1, 320);
      tag = epoch % 3 + 1;
#pragma unroll
      for (int part = 0; part < 3; part++) {
        if (part != 1) {
          const uint32_t xa = base + (2 + part / 2) * GST_BYTES + warp * 2048 + lane * 16;
          mbar_wait(bar_hx + part * 4, 0);
          float s0 = 0.f, s1 = 0.f, q0 = 0.f, q1 = 0.f;
#pragma unroll
          for (int q = 0; q < 4; q++) {
            const uint4 xv = lds4(xa + q * 512);
            const uint32_t u[4] = {xv.x, xv.y, xv.z, xv.w};
#pragma unroll
            for (int e = 0; e < 4; e++) { const float lo = bf_lo(u[e]), hi = bf_hi(u[e]); s0 += lo; s1 += hi; q0 += lo * lo; q1 += hi * hi; }
          }
          s0 += s1; q0 += q1;
#pragma unroll
          for (int o = 16; o > 0; o >>= 1) { s0 += __shfl_xor_sync(0xffffffffu, s0, o); q0 += __shfl_xor_sync(0xffffffffu, q0, o); }
          const float mean = s0 * (1.f / DM);
          float mb, sd;
          ln_scalars(mean, fmaxf(q0 * (1.f / DM) - mean * mean, 0.f), mb, sd);
          if (lane == 0) st_relaxed2(pln + part * 16, __float_as_uint(mb) | tag, __float_as_uint(sd) | tag);
          PROF(1, tid == 0 && part == 2, 4);
        } else {
          float acc[8];
#pragma unroll
          for (int e = 0; e < 8; e++) acc[e] = 0.f;
          const uint32_t wa = stage + (tid >> 2) * 64 + (((tid ^ (tid >> 3)) & 3) << 4), sa = par + (tid >> 3) * 4, sh = (tid & 4) ? 0x3244 : 0x1044;
          mbar_wait(bar_hw, 0);
#pragma unroll
          for (int p = 0; p < 8; p++) {
            const uint4 w = lds4(wa + p * 4096);
            const float s = __uint_as_float(__byte_perm(lds1(sa + p * 128), 0, sh));
            acc[0] += s * bf_lo(w.x); acc[1] += s * bf_hi(w.x); acc[2] += s * bf_lo(w.y); acc[3] += s * bf_hi(w.y);
            acc[4] += s * bf_lo(w.z); acc[5] += s * bf_hi(w.z); acc[6] += s * bf_lo(w.w); acc[7] += s * bf_hi(w.w);
          }
#pragma unroll
          for (int e = 0; e < 4; e++) {
            const bool up = lane & 16;
            acc[e] = (up ? acc[e + 4] : acc[e]) + __shfl_xor_sync(0xffffffffu, up ? acc[e] : acc[e + 4], 16);
          }
#pragma unroll
          for (int e = 0; e < 2; e++) {
            const bool up = lane & 8;
            acc[e] = (up ? acc[e + 2] : acc[e]) + __shfl_xor_sync(0xffffffffu, up ? acc[e] : acc[e + 2], 8);
          }
          {
            const bool up = lane & 4;
            acc[0] = (up ? acc[1] : acc[0]) + __shfl_xor_sync(0xffffffffu, up ? acc[0] : acc[1], 4);
          }
          sts1(par + 1024 + warp * 128 + ((lane & 3) * 8 + (lane >> 2)) * 4, __float_as_uint(acc[0]));
          bar_sync(1, 256);
          if (warp == 0) {
            float s = 0.f;
#pragma unroll
            for (int w8 = 0; w8 < 8; w8++) s += __uint_as_float(lds1(par + 1024 + w8 * 128 + lane * 4));
            st_relaxed(pmod, (__float_as_uint(s) & ~3u) | tag);
          }
          PROF(1, tid == 0, 3);
        }
      }
      {
        uint2 s0 = ld_relaxed2(g_ln1 + (rb * 128 + (tid & 127)) * 4);
        uint4 v[4];
#pragma unroll
        for (int q = 0; q < 4; q++) v[q] = ld_relaxed4(g_modp + q * DM + tid * 4);
        {
          uint32_t n = 0;
          while (!(tag_ok(v[0], tag) && tag_ok(v[1], tag) && tag_ok(v[2], tag) && tag_ok(v[3], tag))) {
#pragma unroll
            for (int q = 0; q < 4; q++)
              if (!tag_ok(v[q], tag)) v[q] = ld_relaxed4(g_modp + q * DM + tid * 4);
            if (((s0.x ^ tag) | (s0.y ^ tag)) & 3u) s0 = ld_relaxed2(g_ln1 + (rb * 128 + (tid & 127)) * 4);
            watchdog(n);
          }
        }
        const uint32_t d = stage + (tid >> 2) * 64 + (tid & 1) * 32 + (tid & 2) * 2;
        sts1(d, pack_bf(1.f + rbf(untag_sum(v[1].x, v[3].x)), 1.f + rbf(untag_sum(v[1].y, v[3].y))));
        sts1(d + 16, pack_bf(1.f + rbf(untag_sum(v[1].z, v[3].z)), 1.f + rbf(untag_sum(v[1].w, v[3].w))));
        sts1(d + 8, pack_bf(untag_sum(v[0].x, v[2].x), untag_sum(v[0].y, v[2].y)));
        sts1(d + 24, pack_bf(untag_sum(v[0].z, v[2].z), untag_sum(v[0].w, v[2].w)));
        if (wg == 0) {
          uint32_t n = 0;
          while (((s0.x ^ tag) | (s0.y ^ tag)) & 3u) { s0 = ld_relaxed2(g_ln1 + (rb * 128 + tid) * 4); watchdog(n); }
          uint32_t ih, il;
          split_inv(bf_hi(s0.y), ih, il);
          sts4(stage + 4096 + tid * 16, make_uint4(__byte_perm(s0.x, 0, 0x3232), ih, il, 0));
        }
        mbar_arrive(bar_mod);
      }
      cluster_wait();
      if (wg == 1) bar_arrive(2, 256);
      mbar_wait(bar_mod, 0);
      PROF(1, tid == 0, 2);
    }

    float f0 = 0.f, f1 = 0.f;
    const uint32_t rempty = lane < 2 ? mapa(bempty, lane & 1) : 0;
    constexpr uint32_t GE = NSLOT * 8 + 32;
    float o[64], s[64];
#pragma unroll 1
    for (int ps = 0; ps < 3; ps++) {
      {
        const uint32_t xt = ps == 1 ? XT1 : XT2, wt = ps == 1 ? WT1 : WT2;
        const int nst = ps == 2 ? 29 : 14;
        if (ps == 0) {
          float ga[64], gb[64];
#pragma unroll
          for (int i = 0; i < 64; i++) { ga[i] = 0.f; gb[i] = 0.f; }
          uint32_t a[2][16];
          const uint32_t l = fresh_lane();
          const uint4 r0 = lds4(stage + 4096 + (warp * 16 + (l >> 2)) * 16), r1 = lds4(stage + 4096 + 128 + (warp * 16 + (l >> 2)) * 16);
          auto transform = [&](int i, uint32_t (&f)[16], uint32_t z) {
            const uint32_t ad = base + (i & 3) * GST_BYTES + wg * 8192 + frag_offset(warp) + z;
            mbar_wait(xfull + (i & 3) * 8, i >> 2);
#pragma unroll
            for (int kk = 0; kk < 4; kk++) ldmatrix4(ad ^ (kk * 32), f[4 * kk], f[4 * kk + 1], f[4 * kk + 2], f[4 * kk + 3]);
#pragma unroll
            for (int kk = 0; kk < 4; kk++) {
              const uint4 m = lds4(stage + (l & 3) * 16 + ((2 * cj + i) & 15) * 256 + kk * 64);
              f[4 * kk] = ln_mod(f[4 * kk], r0.x, r0.y, r0.z, m.x, m.z);
              f[4 * kk + 1] = ln_mod(f[4 * kk + 1], r1.x, r1.y, r1.z, m.x, m.z);
              f[4 * kk + 2] = ln_mod(f[4 * kk + 2], r0.x, r0.y, r0.z, m.y, m.w);
              f[4 * kk + 3] = ln_mod(f[4 * kk + 3], r1.x, r1.y, r1.z, m.y, m.w);
            }
            keep(f);
            mbar_arrive_pred(xempty + (i & 3) * 8, l == 0);
          };
          auto publish = [&](int u, uint32_t (&f)[16]) {
            const uint32_t sc = stage + 8192 + wg * 8192;
#pragma unroll
            for (int kk = 0; kk < 4; kk++) stmatrix4((sc + frag_offset(warp)) ^ (kk * 32), f[4 * kk], f[4 * kk + 1], f[4 * kk + 2], f[4 * kk + 3]);
            __syncwarp();
            const uint32_t src = sc + (warp & 3) * 2048 + l * 16;
            uint8_t* dst = g_act + (uint32_t)(rb * 80 + cj * 2 + u) * UNIT + warp * 2048 + l * 16;
#pragma unroll
            for (int p4 = 0; p4 < 4; p4++) stg4(dst + p4 * 512, lds4(src + p4 * 512));
            __syncwarp();
            if (u == 1) mbar_arrive_pred(bar_hpub, l == 0);
          };
          auto multiply = [&](int i, uint32_t (&f)[16]) {
            mbar_wait(gfull + (i & 3) * 8, i >> 2);
            const uint64_t db = make_desc(base + (i & 3) * GST_BYTES + UNIT, 8192, 1024);
            wg_fence();
#pragma unroll
            for (int kk = 0; kk < 4; kk++) mma256_rs(ga, gb, f[4 * kk], f[4 * kk + 1], f[4 * kk + 2], f[4 * kk + 3], db + kk * 128);
            wg_commit();
          };
          transform(0, a[0], 0); publish(0, a[0]); transform(1, a[1], 0); multiply(0, a[0]); publish(1, a[1]);
#pragma unroll
          for (int i = 1; i < NRS; i++) {
            if (i >= 2) {
              uint32_t z = r0.w;
#pragma unroll
              for (int k = 0; k < 16; k += 2) asm volatile("lop3.b32 %0, %1, %2, %0, 0xA8;" : "+r"(z) : "r"(a[i & 1][k]), "r"(a[i & 1][k + 1]));
              transform(i, a[i & 1], z);
            }
            multiply(i, a[i & 1]);
            wg_wait<1>();
            mbar_arrive_cl(rempty, GE + ((i + 3) & 3) * 8);
          }
          mbar_arrive_pred(bar_pread, l == 0);
#pragma unroll 1
          for (int i = NRS; i < 14; i++) {
            mbar_wait(xfull + (i & 3) * 8, (i >> 2) & 1);
            mbar_wait(gfull + (i & 3) * 8, (i >> 2) & 1);
            const uint32_t xa = base + (i & 3) * GST_BYTES;
            const uint64_t da = make_desc(xa + wg * 8192, 16, 1024), db = make_desc(xa + UNIT, 8192, 1024);
            if (i == 13) bar_sync(2 + wg, 256);
            wg_fence();
#pragma unroll
            for (int kk = 0; kk < 4; kk++) mma256_ss(ga, gb, da + kk * 2, db + kk * 128, 1);
            wg_commit();
            if (i == 13) bar_arrive(3 - wg, 256);
            wg_wait<1>();
            uint32_t z = r0.w;
#pragma unroll
            for (int k = 0; k < 16; k += 2) asm volatile("lop3.b32 %0, %1, %2, %0, 0xA8;" : "+r"(z) : "r"(a[1][k]), "r"(a[1][k + 1]));
            mbar_arrive_cl(rempty, GE + ((i + 3) & 3) * 8 + z);
            mbar_arrive_pred(xempty + ((i + 3) & 3) * 8, l == 0 && i != NRS);
          }
          mbar_wait(xfull + 16, 1);
          mbar_wait(xfull + 24, 1);
          wg_wait<0>();
          keep(ga); keep(gb);
#pragma unroll
          for (int i = 0; i < 64; i++) {
            asm volatile("mov.b32 %0, %1;" : "=f"(s[i]) : "f"(ga[i]));
            asm volatile("mov.b32 %0, %1;" : "=f"(o[i]) : "f"(gb[i]));
          }
        } else {
          float ga[64], gb[64];
#pragma unroll
          for (int i = 0; i < 64; i++) {
            asm volatile("mov.b32 %0, %1;" : "=f"(ga[i]) : "f"(s[i]));
            asm volatile("mov.b32 %0, %1;" : "=f"(gb[i]) : "f"(o[i]));
          }
#pragma unroll 1
          for (int i = 0; i < nst; i++) {
            mbar_wait(gfull + (i & 3) * 8, (i >> 2) & 1);
            const uint64_t da = make_desc(base + unit_of(xt, i & 3) + wg * 8192, 16, 1024), db = make_desc(base + unit_of(wt, i & 3), 8192, 1024);
            if (i == nst - 1) bar_sync(2 + wg, 256);
            wg_fence();
#pragma unroll
            for (int kk = 0; kk < 4; kk++) mma256_ss(ga, gb, da + kk * 2, db + kk * 128, kk ? 1 : i);
            wg_commit();
            if (i == nst - 1) bar_arrive(3 - wg, 256);
            wg_wait<1>();
            mbar_arrive_cl(rempty, GE + ((i + 3) & 3) * 8, i != 0);
            PROF(4, tid == 0 && (i & 3) == 0, 40 + (ps - 1) * 4 + i / 4);
          }
          wg_wait<0>();
          keep(ga); keep(gb);
#pragma unroll
          for (int i = 0; i < 64; i++) {
            asm volatile("mov.b32 %0, %1;" : "=f"(s[i]) : "f"(ga[i]));
            asm volatile("mov.b32 %0, %1;" : "=f"(o[i]) : "f"(gb[i]));
          }
        }
        if (ps == 2) break;
        mbar_arrive_cl(rempty, GE + 8);
      }
      const uint32_t qw = base + wg * 8192, qt = QT >> (16 * ps), at = ps ? AT1 : AT0;
      {
        const uint32_t wt = ps ? WT1 : WT0;
        const uint64_t da0 = make_desc(qw + unit_of(qt, 2), 16, 1024), da1 = make_desc(qw + unit_of(qt, 3), 16, 1024);
        const uint64_t db0 = make_desc(base + unit_of(wt, 2), 8192, 1024), db1 = make_desc(base + unit_of(wt, 3), 8192, 1024);
        mbar_wait(gfull + 16, 1);
        mbar_wait(gfull + 24, 1);
        bar_sync(2 + wg, 256);
        wg_fence();
#pragma unroll
        for (int kk = 0; kk < 8; kk++) mma_ss<1>(s, (kk < 4 ? da0 : da1) + (kk & 3) * 2, (kk < 4 ? db0 : db1) + (kk & 3) * 128, 1);
        wg_commit();
        bar_arrive(3 - wg, 256);
        mbar_wait(ps == 0 ? bar_pread : bar_ofree + 8, 0);
        mbar_wait(bfull, 0);
        wg_wait<0>();
        keep(s);
        PROF(2, tid == 0, 8 + ps * 8);
        store_chunk<0>(s, qw + unit_of(qt, 0) + frag_offset(warp));
        store_chunk<1>(s, qw + unit_of(qt, 1) + frag_offset(warp));
        fence_async_smem();
        bar_sync(2 + wg, 256);
        wg_fence();
        issue_qk(s, qw + unit_of(qt, 0), qw + unit_of(qt, 1), base + unit_of(at, 0));
        wg_commit();
#pragma unroll
        for (int kk = 0; kk < 8; kk++) mma_ss<1>(o, (kk < 4 ? da0 : da1) + (kk & 3) * 2, (kk < 4 ? db0 : db1) + UNIT / 16 + (kk & 3) * 128, 1);
        wg_commit();
        bar_arrive(3 - wg, 256);
        wg_wait<1>();
        keep(s);
        mbar_arrive_cl(rempty, 0);
      }
      PROF(4, tid == 0 && ps == 1, 61);
      float l0 = 0.25f, l1 = 0.25f;
      auto step = [&](auto odd_c, const int j, uint32_t (&pw)[32], uint32_t (&pr)[32]) {
        constexpr bool ODD = decltype(odd_c)::value;
        const bool first = !ODD && (j & 2) == 0, last = ODD && j == 7;
        const uint32_t ph = (j >> 1) & 1;
        float i0, i1, a0, a1;
        if (first) { i0 = inv_quad_sum(l0); i1 = inv_quad_sum(l1); l0 = 0.f; l1 = 0.f; }
        bool redo = !ODD && (j | ps) == 0, again = false;
        while (true) {
          if (redo) {
            float m0 = fmaxf(s[0], s[1]), m1 = fmaxf(s[2], s[3]);
#pragma unroll
            for (int i = 1; i < 16; i++) { m0 = fmaxf(m0, fmaxf(s[4 * i], s[4 * i + 1])); m1 = fmaxf(m1, fmaxf(s[4 * i + 2], s[4 * i + 3])); }
            m0 = fmaxf(m0, __shfl_xor_sync(0xffffffffu, m0, 1)); m1 = fmaxf(m1, __shfl_xor_sync(0xffffffffu, m1, 1));
            m0 = fmaxf(m0, __shfl_xor_sync(0xffffffffu, m0, 2)); m1 = fmaxf(m1, __shfl_xor_sync(0xffffffffu, m1, 2));
            m0 *= SCL2; m1 *= SCL2;
            if (!first) {
              m0 = fmaxf(m0, f0); m1 = fmaxf(m1, f1);
              const float c0 = ex2(f0 - m0), c1 = ex2(f1 - m1);
              l0 *= c0; l1 *= c1;
              wg_wait<0>();
              keep(o);
#pragma unroll
              for (int i = 0; i < 16; i++) { o[4 * i] *= c0; o[4 * i + 1] *= c0; o[4 * i + 2] *= c1; o[4 * i + 3] *= c1; }
            }
            f0 = m0; f1 = m1;
          }
          float b0 = 0.f, b1 = 0.f;
          a0 = 0.f; a1 = 0.f;
#pragma unroll
          for (int i = 0; i < 16; i++) {
            const float e0 = ex2(fmaf(s[4 * i], SCL2, -f0)), e1 = ex2(fmaf(s[4 * i + 1], SCL2, -f0));
            const float e2 = ex2(fmaf(s[4 * i + 2], SCL2, -f1)), e3 = ex2(fmaf(s[4 * i + 3], SCL2, -f1));
            a0 += e0; b0 += e1; a1 += e2; b1 += e3;
            pw[2 * i] = pack_bf(e0, e1); pw[2 * i + 1] = pack_bf(e2, e3);
            if (i == VREL) {
#pragma unroll
              for (int k = 0; k < 2 * VREL + 2; k++) asm volatile("" : "+r"(pw[k])::"memory");
              mbar_wait(bfull + (ODD ? 24 : 8), ph);
              wg_wait<0>();
              mbar_arrive_cl(rempty, ODD ? 16 : (j ? 0 : GE + 16), !again);
              if (!ODD) mbar_arrive_cl(rempty, GE + 24, !again && j == 0);
#pragma unroll
              for (int k = 4 * VREL + 4; k < 64; k++) asm volatile("" : "+f"(s[k])::"memory");
            }
          }
          a0 += b0; a1 += b1;
          if (redo) break;
          redo = __any_sync(0xffffffffu, !(a0 + a1 < 0x1p70f));
          if (first) {
            uint32_t m0 = __ballot_sync(0xffffffffu, a0 > 0x1p-50f), m1 = __ballot_sync(0xffffffffu, a1 > 0x1p-50f);
            m0 |= m0 >> 1; m1 |= m1 >> 1; m0 |= m0 >> 2; m1 |= m1 >> 2;
            redo = redo || (m0 & m1 & 0x11111111u) != 0x11111111u;
          }
          if (!redo) break;
          again = true;
        }
        l0 += a0; l1 += a1;
        keep(pw);
        keep(o);
        const uint32_t qo = qt >> (j ? 0 : 8);
        if (first) store_chunk<0>(o, i0, i1, qw + unit_of(qo, 0) + frag_offset(warp));
        keep(o);
        bar_sync(2 + wg, 256);
        if (!last) {
          const uint32_t qn = qt >> (j >= 3 ? 8 : 0);
          wg_fence();
          issue_qk(s, qw + unit_of(qn, 0), qw + unit_of(qn, 1), base + unit_of(at, ODD ? 3 : 1));
          wg_commit();
          mbar_wait(bfull + (ODD ? 0 : 16), ODD ? ph ^ 1 : ph);
        }
        if (first) { store_chunk<1>(o, i0, i1, qw + unit_of(qo, 1) + frag_offset(warp)); keep(o); }
        wg_fence();
        issue_pv(o, pw, base + unit_of(at, ODD ? (last ? 3 : 0) : 2), !first);
        wg_commit();
        bar_arrive(3 - wg, 256);
        if (first) { fence_async_smem(); mbar_arrive_pred(bar_ofull + wg * 8, j); PROF(2, tid == 0 && j, 9 + ps * 8); }
        wg_wait<1>();
        keep(s);
        mbar_arrive_cl(rempty, ODD ? 24 : 8, !last);
        PROF(4, tid == 0 && ps == 1, 51 + j);
      };
      uint32_t pa[32], pb[32];
#pragma unroll 1
      for (int j = 0; j < 8; j += 2) {
        step(std::false_type{}, j, pa, pb);
        step(std::true_type{}, j + 1, pb, pa);
      }
      {
        const float i0 = inv_quad_sum(l0), i1 = inv_quad_sum(l1);
        wg_wait<0>();
        keep(o);
        mbar_arrive_cl(rempty, 24);
        store_chunk<0>(o, i0, i1, qw + unit_of(qt, 2) + frag_offset(warp));
        store_chunk<1>(o, i0, i1, qw + unit_of(qt, 3) + frag_offset(warp));
        fence_async_smem();
        mbar_arrive(bar_ofull + wg * 8);
      }
      PROF(2, tid == 0, 10 + ps * 8);
    }

    const int ln = fresh_lane(), g = ln >> 2, tq = ln & 3, ct = warp * 32 + ln;
    const bool lane0 = ln == 0;
    const int lrow0 = warp * 16 + g;
    const int grow0 = rb * 128 + lrow0;
    const uint32_t res = base + OFF_RES, trow = res + wg * 8192 + frag_offset(warp);
    uint32_t xr[32];
    {
      const uint64_t da = make_desc(base + wg * 8192, 16, 1024), db = make_desc(base, 8192, 1024);
      constexpr int U = UNIT / 16;
      constexpr int XU[3] = {9, 12, 13}, WU[3] = {10, 0, 2};
#define HALF_STAGE(acc, st, hf) _Pragma("unroll") for (int kk = 0; kk < 4; kk++) mma_ss<1>(acc, da + XU[st] * U + kk * 2, db + (WU[st] + hf) * U + kk * 128, 1)
      mbar_arrive_pred(bar_ring, lane0);
      PROF(10, ct == PT, 19);
      mbar_wait(gfull + 8, 1);
      mbar_wait(gfull + 16, 1);
      bar_sync(2 + wg, 256);
      wg_fence();
      HALF_STAGE(o, 0, 1);
      HALF_STAGE(o, 1, 1);
      wg_commit();
      mbar_wait(gfull + 24, 1);
      wg_fence();
      HALF_STAGE(o, 2, 1);
      wg_commit();
      bar_arrive(3 - wg, 256);
      cluster_arrive();
      mbar_wait(bar_par, 0);
      uint32_t* xo = g_xch + ((size_t)b * 8 * 256 + ct) * 4;
      const uint32_t* xi = g_xch + ((size_t)(b ^ 2) * 8 * 256 + ct) * 4;
      const uint32_t par1 = (~lds1(par + PAR_CONST + 48) & 1) << 16;
      wg_wait<0>();
      keep(o);
      mbar_arrive_pred(bar_ring + 8, lane0);
      PROF(8, ct == PT, 20);
      uint32_t w[32];
      pack_p(o, w);
#pragma unroll
      for (int i = 0; i < 8; i++) w[4 * i] = (w[4 * i] & ~0x10000u) | par1;
      keep(w);
#pragma unroll
      for (int i = 0; i < 8; i++) st_b128(xo + i * 1024, w[4 * i], w[4 * i + 1], w[4 * i + 2], w[4 * i + 3]);
      PROF(8, ct == PT, 21);
      bar_sync(2 + wg, 256);
      wg_fence();
      HALF_STAGE(s, 0, 0);
      wg_commit();
      uint4 v[8];
#pragma unroll
      for (int i = 0; i < 8; i++) v[i] = ld_b128(xi + i * 1024);
      mbar_wait(bar_xres, 0);
      wg_fence();
      HALF_STAGE(s, 1, 0);
      HALF_STAGE(s, 2, 0);
      wg_commit();
      bar_arrive(3 - wg, 256);
#pragma unroll
      for (int i = 0; i < 16; i += 2) ldmatrix4((trow ^ ((i & 7) << 4)) + (i >> 3) * 16384, xr[2 * i], xr[2 * i + 1], xr[2 * i + 2], xr[2 * i + 3]);
      uint32_t n = 0;
      bool ok;
      do {
        ok = true;
#pragma unroll
        for (int i = 0; i < 8; i++)
          if ((v[i].x & 0x10000u) != par1) { v[i] = ld_b128(xi + i * 1024); ok = false; }
        watchdog(n);
      } while (!ok);
      PROF(8, ct == PT, 22);
      wg_wait<0>();
      keep(s);
      mbar_arrive_pred(bar_ring + 16, lane0);
      PROF(10, ct == PT, 23);
#pragma unroll
      for (int i = 0; i < 8; i++) {
        s[8 * i] += bf_lo(v[i].x); s[8 * i + 1] += __uint_as_float(v[i].x & 0xfffe0000u); s[8 * i + 2] += bf_lo(v[i].y); s[8 * i + 3] += bf_hi(v[i].y);
        s[8 * i + 4] += bf_lo(v[i].z); s[8 * i + 5] += bf_hi(v[i].z); s[8 * i + 6] += bf_lo(v[i].w); s[8 * i + 7] += bf_hi(v[i].w);
      }
    }
    float su0 = 0.f, su1 = 0.f, sq0 = 0.f, sq1 = 0.f, dt0 = 0.f, dt1 = 0.f;
#pragma unroll
    for (int i = 0; i < 16; i++) {
      const uint4 pv = lds4(par + PAR_T1 + i * 64 + tq * 16);
      const uint32_t u0 = hadd2(xr[2 * i], hmul2(pv.x, pack_bf(s[4 * i], s[4 * i + 1])));
      const uint32_t u1 = hadd2(xr[2 * i + 1], hmul2(pv.x, pack_bf(s[4 * i + 2], s[4 * i + 3])));
      xr[2 * i] = u0; xr[2 * i + 1] = u1;
      const float a = bf_lo(u0), c = bf_hi(u0), d = bf_lo(u1), e = bf_hi(u1);
      su0 += a + c; su1 += d + e;
      sq0 = fmaf(a, a, fmaf(c, c, sq0)); sq1 = fmaf(d, d, fmaf(e, e, sq1));
      dt0 = fmaf(a, __uint_as_float(pv.z), fmaf(c, __uint_as_float(pv.w), dt0));
      dt1 = fmaf(d, __uint_as_float(pv.z), fmaf(e, __uint_as_float(pv.w), dt1));
    }
    {
      const bool odd = tq & 1;
      float su = (odd ? su1 : su0) + __shfl_xor_sync(0xffffffffu, odd ? su0 : su1, 1);
      float sq = (odd ? sq1 : sq0) + __shfl_xor_sync(0xffffffffu, odd ? sq0 : sq1, 1);
      float dt = (odd ? dt1 : dt0) + __shfl_xor_sync(0xffffffffu, odd ? dt0 : dt1, 1);
      su += __shfl_xor_sync(0xffffffffu, su, 2); sq += __shfl_xor_sync(0xffffffffu, sq, 2); dt += __shfl_xor_sync(0xffffffffu, dt, 2);
      if (tq < 2) st_b128(g_stats + ((size_t)cj * SEQ + grow0 + tq * 8) * 4, __float_as_uint(su), __float_as_uint(sq), __float_as_uint(dt), tag);
    }
    PROF(8, ct == PT, 29);
    uint32_t mm, ih, il;
    float rbest;
    {
      const uint32_t* sp = g_stats + ((size_t)(tq >> 1) * 4 * SEQ + grow0 + (tq & 1) * 8) * 4;
      uint4 v0 = ld_b128(sp), v1 = ld_b128(sp + SEQ * 4), v2 = ld_b128(sp + SEQ * 8), v3 = ld_b128(sp + SEQ * 12);
#pragma unroll
      for (int i = 0; i < 16; i += 2) stmatrix4((trow ^ ((i & 7) << 4)) + (i >> 3) * 16384, xr[2 * i], xr[2 * i + 1], xr[2 * i + 2], xr[2 * i + 3]);
      const uint4 cst = lds4(par + PAR_CONST);
      const float A1 = __uint_as_float(cst.x) + __uint_as_float(cst.z), A2 = __uint_as_float(cst.y) + __uint_as_float(cst.w);
      uint32_t n = 0;
      while (v0.w != tag || v1.w != tag || v2.w != tag || v3.w != tag) {
        if (v0.w != tag) v0 = ld_b128(sp);
        if (v1.w != tag) v1 = ld_b128(sp + SEQ * 4);
        if (v2.w != tag) v2 = ld_b128(sp + SEQ * 8);
        if (v3.w != tag) v3 = ld_b128(sp + SEQ * 12);
        watchdog(n);
      }
      __syncwarp();
      PROF(8, ct == PT, 30);
      float su = (__uint_as_float(v0.x) + __uint_as_float(v1.x)) + (__uint_as_float(v2.x) + __uint_as_float(v3.x));
      float sq = (__uint_as_float(v0.y) + __uint_as_float(v1.y)) + (__uint_as_float(v2.y) + __uint_as_float(v3.y));
      float dt = (__uint_as_float(v0.z) + __uint_as_float(v1.z)) + (__uint_as_float(v2.z) + __uint_as_float(v3.z));
      su += __shfl_xor_sync(0xffffffffu, su, 2); sq += __shfl_xor_sync(0xffffffffu, sq, 2); dt += __shfl_xor_sync(0xffffffffu, dt, 2);
      const float m = su * (1.f / DM);
      float mb, sd;
      ln_scalars(m, fmaxf(sq * (1.f / DM) - m * m, 0.f), mb, sd);
      const float inv = 1.f / sd;
      rbest = (dt - mb * A1) * inv + A2;
      mm = pack_bf(mb, mb);
      ih = pack_bf(inv, inv);
      const float lo = inv - bf_lo(ih);
      il = pack_bf(lo, lo);
    }
    int ibest;
    {
      const uint32_t bits = __float_as_uint(rbest) & ~3u, key = (int)bits < 0 ? ~bits : bits | 0x80000000u;
      const uint32_t kmax = __reduce_max_sync(0xffffffffu, key);
      const uint32_t row = __reduce_min_sync(0xffffffffu, key == kmax ? lrow0 + (tq & 1) * 8 : 255);
      if (lane0) sts2(par + PAR_RED + warp * 8, kmax, row);
      PROF(8, ct == PT, 38);
      bar_sync(1, 256);
      const uint2 cv = lds2(par + PAR_RED + (ln & 7) * 8);
      const uint32_t k2 = __reduce_max_sync(0xffffffffu, cv.x);
      ibest = __reduce_min_sync(0xffffffffu, cv.x == k2 ? cv.y : 255);
      if (ct < 16) st_relaxed2(g_cand + (cj * 16 + ct) * 32 + rb * 2, (k2 & ~3u) | tag, ((rb * 128 + ibest) << 2) | tag);
    }
    PROF(8, ct == PT, 39);
    if ((ibest >> 4) == warp) {
      const int src = (ibest & 7) * 4 + ((ibest >> 3) & 1), ch = g * 2;
      const uint32_t cm = __shfl_sync(0xffffffffu, mm, src), ch_ = __shfl_sync(0xffffffffu, ih, src), cl = __shfl_sync(0xffffffffu, il, src);
      const uint32_t xa = res + (ch >> 3) * 16384 + ibest * 128 + (((ch & 7) ^ (ibest & 7)) << 4) + tq * 4;
      const uint32_t x0 = lds1(xa), x1 = lds1(xa ^ 16);
      const uint2 p0 = lds2(par + PAR_T2 + ch * 32 + tq * 8), p1 = lds2(par + PAR_T2 + ch * 32 + 32 + tq * 8);
      uint32_t* dst = g_row + rb * 2 * DM + cj * 128 + ln * 4;
      st_pairs(dst, ln_mod(x0, cm, ch_, cl, p0.x, p0.y), ln_mod(x1, cm, ch_, cl, p1.x, p1.y), tag);
      st_pairs(dst + DM, x0, x1, tag);
      __syncwarp();
    }
    PROF(8, ct == PT, 37);
    const uint32_t* inbox = g_cand + b * 32 + (ln & 15) * 2;
    uint2 cv = ld_relaxed2(inbox);
    uint32_t wf[128];
    const uint32_t frow = (ln & 7) + (ln >> 4) * 8;
    const uint32_t wfo = base + (warp & 1) * 8192 + frow * 64 + ((((ln >> 3) & 1) ^ ((frow >> 1) & 3)) << 4);
    if (b < NFFN) {
#pragma unroll
      for (int m = 0; m < 2; m++) {
        const uint32_t wfa = wfo + unit_of(m ? FT_U : FT_G, warp >> 1);
        mbar_wait(bar_box + (m * 4 + (warp >> 1)) * 8, 0);
#pragma unroll
        for (int f = 0; f < 16; f++) {
          const int r = ((f >> 1) * 4 + m * 2 + (f & 1)) * 4;
          ldmatrix4t((wfa ^ ((f & 1) * 32)) + (f >> 1) * 1024, wf[r], wf[r + 1], wf[r + 2], wf[r + 3]);
        }
      }
    }
    PROF(8, ct == PT, 31);
    uint32_t kwin; int iwin;
    uint4 hv[8];
    uint32_t wd[64];
    const uint32_t wda = base + unit_of(FT_D, warp >> 1) + (warp & 1) * 8192 + frow * 128 + ((((ln >> 3) & 1) ^ (ln & 7)) << 4);
#define LOAD_WD(f) ldmatrix4t((wda ^ ((((f) >> 1) & 3) * 32)) + ((f) >> 3) * 4096 + ((f) & 1) * 2048, wd[4 * (f)], wd[4 * (f) + 1], wd[4 * (f) + 2], wd[4 * (f) + 3])
    {
      uint32_t n = 0;
      int cur = -1;
      while (true) {
        const bool valid = !(((cv.x ^ tag) | (cv.y ^ tag)) & 3u);
        const uint32_t key = valid ? cv.x : 0u;
        kwin = __reduce_max_sync(0xffffffffu, key);
        const int src = (__ffs(__ballot_sync(0xffffffffu, key == kwin)) - 1) & 15;
        if (kwin && src != cur) {
          cur = src;
#pragma unroll
          for (int i = 0; i < 8; i++) hv[i] = ld_pairs(g_row + cur * 2 * DM + warp * 128 + i * 16 + tq * 4);
        }
        if (__all_sync(0xffffffffu, valid)) break;
        cv = ld_relaxed2(inbox);
        watchdog(n);
      }
      iwin = __shfl_sync(0xffffffffu, cv.y, cur) >> 2;
    }
    PROF(8, ct == PT, 32);
    const uint32_t* wrow = g_row + (iwin >> 7) * 2 * DM;
    if (b < NFFN) {
      {
        uint32_t n = 0;
        bool ok;
        do {
          ok = true;
#pragma unroll
          for (int i = 0; i < 8; i++)
            if (hv[i].y != tag || hv[i].w != tag) { hv[i] = ld_pairs(wrow + warp * 128 + i * 16 + tq * 4); ok = false; }
          watchdog(n);
        } while (!ok);
      }
      __syncwarp();
      PROF(8, ct == PT, 33);
      float d[8][4];
#pragma unroll
      for (int i = 0; i < 8; i++) { d[i][0] = 0.f; d[i][1] = 0.f; d[i][2] = 0.f; d[i][3] = 0.f; }
#pragma unroll
      for (int ks = 0; ks < 8; ks++) {
#pragma unroll
        for (int mt = 0; mt < 4; mt++) {
          const int r = ks * 16 + mt * 4;
          mma16816(d[mt + (ks & 1) * 4], wf[r], wf[r + 1], wf[r + 2], wf[r + 3], hv[ks].x, hv[ks].z);
        }
      }
      if (tq == 0) {
        const uint32_t dst = base + unit_of(FT_G, warp >> 1) + (warp & 1) * 8192 + g * 32;
        sts4(dst, make_uint4(__float_as_uint(d[0][0] + d[4][0]), __float_as_uint(d[0][2] + d[4][2]), __float_as_uint(d[1][0] + d[5][0]), __float_as_uint(d[1][2] + d[5][2])));
        sts4(dst + 16, make_uint4(__float_as_uint(d[2][0] + d[6][0]), __float_as_uint(d[2][2] + d[6][2]), __float_as_uint(d[3][0] + d[7][0]), __float_as_uint(d[3][2] + d[7][2])));
      }
      bar_sync(1, 256);
      uint32_t ab[4];
      {
        float G = 0.f, U = 0.f;
        const uint32_t src = base + (ln & 7) * 32 + (ln >> 3) * 4;
#pragma unroll
        for (int w8 = 0; w8 < 8; w8++) {
          const uint32_t a = src + ((FT_G >> (w8 >> 1) * 4) & 15) * UNIT + (w8 & 1) * 8192;
          G += __uint_as_float(lds1(a)); U += __uint_as_float(lds1(a + 16));
        }
        mbar_wait(bar_box + (8 + (warp >> 1)) * 8, 0);
#pragma unroll
        for (int f = 0; f < 16; f++) LOAD_WD(f);
        const float act = rbf(silu_f(rbf(G))) * rbf(U);
        const uint32_t pk = pack_bf(act, __shfl_down_sync(0xffffffffu, act, 1));
#pragma unroll
        for (int i = 0; i < 4; i++) ab[i] = __shfl_sync(0xffffffffu, pk, i * 8 + tq * 2);
      }
      PROF(8, ct == PT, 34);
#pragma unroll
      for (int mt = 0; mt < 8; mt++) {
        d[mt][0] = 0.f; d[mt][1] = 0.f; d[mt][2] = 0.f; d[mt][3] = 0.f;
        mma16816(d[mt], wd[mt * 8], wd[mt * 8 + 1], wd[mt * 8 + 2], wd[mt * 8 + 3], ab[0], ab[1]);
        mma16816(d[mt], wd[mt * 8 + 4], wd[mt * 8 + 5], wd[mt * 8 + 6], wd[mt * 8 + 7], ab[2], ab[3]);
      }
#pragma unroll
      for (int i = 0; i < 4; i++) {
        const int m4 = (i >> 1) * 4, e = (i & 1) * 2;
        const float y = (tq & 2) ? ((tq & 1) ? d[m4 + 3][e] : d[m4 + 2][e]) : ((tq & 1) ? d[m4 + 1][e] : d[m4][e]);
        st_relaxed(g_ypart + ((size_t)(warp * 16 + (m4 + tq) * 2 + (i & 1)) * NFFN + b) * 8 + g, tagf(y, tag));
      }
      PROF(8, ct == PT, 35);
    }
    uint2 fh = make_uint2(0, 0), fx = make_uint2(0, 0);
    const uint32_t* fsrc = wrow + (b >> 1) * 16 + (ct & 3) * 4 + (b & 1) * 2;
    if (ct < 4) { fh = ld_pair(fsrc); fx = ld_pair(fsrc + DM); }
    {
      const uint32_t mm0 = __shfl_sync(0xffffffffu, mm, ln & ~1), mm1 = __shfl_sync(0xffffffffu, mm, ln | 1);
      const uint32_t ih0 = __shfl_sync(0xffffffffu, ih, ln & ~1), ih1 = __shfl_sync(0xffffffffu, ih, ln | 1);
      const uint32_t il0 = __shfl_sync(0xffffffffu, il, ln & ~1), il1 = __shfl_sync(0xffffffffu, il, ln | 1);
#pragma unroll 2
      for (int i = 0; i < 16; i += 2) {
        const uint32_t ta = (trow ^ ((i & 7) << 4)) + (i >> 3) * 16384;
        uint32_t x[4];
        ldmatrix4(ta, x[0], x[1], x[2], x[3]);
#pragma unroll
        for (int u = 0; u < 2; u++) {
          const uint2 pv = lds2(par + PAR_T2 + (i + u) * 32 + tq * 8);
          const uint32_t gb = lds1(par + PAR_T1 + (i + u) * 64 + tq * 16 + 4);
          x[2 * u] = hadd2(x[2 * u], hmul2(gb, ln_mod(x[2 * u], mm0, ih0, il0, pv.x, pv.y)));
          x[2 * u + 1] = hadd2(x[2 * u + 1], hmul2(gb, ln_mod(x[2 * u + 1], mm1, ih1, il1, pv.x, pv.y)));
        }
        stmatrix4(ta, x[0], x[1], x[2], x[3]);
      }
      __syncwarp();
      const int wrow0 = warp * 16;
#pragma unroll
      for (int p = 0; p < 8; p++) {
        const int row = 2 * p + (ln >> 4), ch = ln & 15;
        const uint4 v = lds4(res + (ch >> 3) * 16384 + (wrow0 + row) * 128 + (((ch & 7) ^ (row & 7)) << 4));
        if (rb * 128 + wrow0 + row != iwin) *reinterpret_cast<uint4*>(P.out + (size_t)(rb * 128 + wrow0 + row) * DM + cj * 128 + ch * 8) = v;
      }
    }
    PROF(8, ct == PT, 11);
    {
      float y0 = 0.f, y1 = 0.f, y2 = 0.f, y3 = 0.f;
      const float rwin = __uint_as_float(((int)kwin < 0 ? kwin & 0x7fffffffu : ~kwin) & ~3u);
      const float rs = rbf(1.f / (1.f + __expf(-rbf(rwin))));
      if (ct < 4) {
        uint32_t n = 0;
        while (fh.y != tag || fx.y != tag) { fh = ld_pair(fsrc); fx = ld_pair(fsrc + DM); watchdog(n); }
      }
      if (ct < 2 * NFFN) {
        const uint4 v = poll4(g_ypart + (size_t)b * NFFN * 8 + ct * 4, tag);
        y0 = __uint_as_float(v.x & ~3u); y1 = __uint_as_float(v.y & ~3u); y2 = __uint_as_float(v.z & ~3u); y3 = __uint_as_float(v.w & ~3u);
      }
      __syncwarp();
      PROF(8, ct == PT, 5);
      const bool u1 = ln & 2, u2 = ln & 4;
      y0 = (u1 ? y2 : y0) + __shfl_xor_sync(0xffffffffu, u1 ? y0 : y2, 2);
      y1 = (u1 ? y3 : y1) + __shfl_xor_sync(0xffffffffu, u1 ? y1 : y3, 2);
      y0 = (u2 ? y1 : y0) + __shfl_xor_sync(0xffffffffu, u2 ? y0 : y1, 4);
      y0 += __shfl_xor_sync(0xffffffffu, y0, 8);
      y0 += __shfl_xor_sync(0xffffffffu, y0, 16);
      if (ln < 8) sts1(par + PAR_RED + 64 + warp * 32 + ((ln & 1) * 4 + (ln & 2) + (ln >> 2)) * 4, __float_as_uint(y0));
      bar_sync(1, 256);
      PROF(8, ct == PT, 7);
      if (ct < 4) {
        float ya = 0.f, yb = 0.f;
#pragma unroll
        for (int w8 = 0; w8 < 7; w8++) {
          const uint2 v = lds2(par + PAR_RED + 64 + w8 * 32 + ct * 8);
          ya += __uint_as_float(v.x); yb += __uint_as_float(v.y);
        }
        const uint2 gv = lds2(par + PAR_CONST + 16 + ct * 8);
        const uint32_t upd = hmul2(pack_bf(ya, yb), pack_bf(rs, rs));
        *reinterpret_cast<uint32_t*>(P.out + (size_t)iwin * DM + b * 8 + ct * 2) =
            hadd2(fx.x, hmul2(__byte_perm(gv.x, gv.y, 0x7632), hadd2(fh.x, upd)));
      }
      if (b == 0 && ct == 0) st_relaxed(&g_epoch, lds1(par + PAR_CONST + 48) + 1);
    }
    PROF(15, ct == 0, 36);
    cluster_wait();
  }
}

typedef CUresult (*EncodeFn)(CUtensorMap*, CUtensorMapDataType, cuuint32_t, void*, const cuuint64_t*, const cuuint64_t*,
                             const cuuint32_t*, const cuuint32_t*, CUtensorMapInterleave, CUtensorMapSwizzle,
                             CUtensorMapL2promotion, CUtensorMapFloatOOBfill);

void map2d(EncodeFn enc, CUtensorMap* m, const void* p, uint64_t rows, uint64_t cols, uint32_t brows) {
  cuuint64_t dims[2] = {cols, rows}, strides[1] = {cols * 2};
  cuuint32_t box[2] = {64, brows}, es[2] = {1, 1};
  enc(m, CU_TENSOR_MAP_DATA_TYPE_BFLOAT16, 2, const_cast<void*>(p), dims, strides, box, es, CU_TENSOR_MAP_INTERLEAVE_NONE,
      CU_TENSOR_MAP_SWIZZLE_128B, CU_TENSOR_MAP_L2_PROMOTION_L2_256B, CU_TENSOR_MAP_FLOAT_OOB_FILL_NONE);
}
void map2d_narrow(EncodeFn enc, CUtensorMap* m, const void* p, uint64_t rows, uint64_t cols) {
  cuuint64_t dims[2] = {cols, rows}, strides[1] = {cols * 2};
  cuuint32_t box[2] = {32, 256}, es[2] = {1, 1};
  enc(m, CU_TENSOR_MAP_DATA_TYPE_BFLOAT16, 2, const_cast<void*>(p), dims, strides, box, es, CU_TENSOR_MAP_INTERLEAVE_NONE,
      CU_TENSOR_MAP_SWIZZLE_64B, CU_TENSOR_MAP_L2_PROMOTION_L2_64B, CU_TENSOR_MAP_FLOAT_OOB_FILL_NONE);
}
void map3d(EncodeFn enc, CUtensorMap* m, const void* p, uint64_t rows, uint64_t cols, uint32_t brows, uint32_t nch) {
  cuuint64_t dims[3] = {64, rows, cols / 64}, strides[2] = {cols * 2, 128};
  cuuint32_t box[3] = {64, brows, nch}, es[3] = {1, 1, 1};
  enc(m, CU_TENSOR_MAP_DATA_TYPE_BFLOAT16, 3, const_cast<void*>(p), dims, strides, box, es, CU_TENSOR_MAP_INTERLEAVE_NONE,
      CU_TENSOR_MAP_SWIZZLE_128B, CU_TENSOR_MAP_L2_PROMOTION_L2_256B, CU_TENSOR_MAP_FLOAT_OOB_FILL_NONE);
}

}

extern "C" void kernel_launch(void* const* d_in, const int* in_sizes, int n_in, void* d_out, int out_size) {
  (void)in_sizes; (void)n_in; (void)out_size;
  static EncodeFn enc = nullptr;
  if (!enc) {
    void* fn = nullptr;
    cudaDriverEntryPointQueryResult st;
    cudaGetDriverEntryPoint("cuTensorMapEncodeTiled", &fn, cudaEnableDefault, &st);
    enc = (EncodeFn)fn;
    cudaFuncSetAttribute(fused_kernel, cudaFuncAttributeMaxDynamicSharedMemorySize, SMEM_BYTES);
  }
  Maps maps;
  map2d(enc, &maps.x, d_in[0], SEQ, DM, 128);
  map3d(enc, &maps.wq, d_in[3], DM, NQ, 64, 2);
  map3d(enc, &maps.k, d_in[1], 4 * SK, 128, 128, 1);
  map3d(enc, &maps.v, d_in[2], 4 * SK, 128, 128, 1);
  map3d(enc, &maps.wo, d_in[4], NQ, DM, 64, 2);
  map2d_narrow(enc, &maps.wg, d_in[7], DM, FF);
  map2d_narrow(enc, &maps.wu, d_in[8], DM, FF);
  map3d(enc, &maps.wd, d_in[9], FF, DM, 32, 4);
  map2d_narrow(enc, &maps.wm, d_in[11], DM, NMOD);
  Ptrs p;
  p.x = (const __nv_bfloat16*)d_in[0];
  p.w_r = (const __nv_bfloat16*)d_in[6];
  p.w_gate = (const __nv_bfloat16*)d_in[7];
  p.w_up = (const __nv_bfloat16*)d_in[8];
  p.w_down = (const __nv_bfloat16*)d_in[9];
  p.c = (const __nv_bfloat16*)d_in[10];
  p.w_mod = (const __nv_bfloat16*)d_in[11];
  p.out = (__nv_bfloat16*)d_out;
  fused_kernel<<<NMAIN + NHELP, 384, SMEM_BYTES>>>(maps, p);
}
```

```cpp
#include <cuda_runtime.h>
#include <cuda_bf16.h>
#include <cuda.h>
#include <stdint.h>
#include <type_traits>

#define HD 1
#define HDX 2
#define XF 4
#define XE 32
#define XR 0
#define PF2 1
#define PF2T 1
#define NRS 6
#define FPACE 2
#define GOST 24
#define WB 2
#define WN 16
#define RES0 17
#define RES1 20
#define HU 32
#define VREL 7
#define E0 3

namespace {

constexpr int SEQ = 2048, DM = 1024, NQ = 4096, SK = 2048, WIN = 512, FF = 3584, NMOD = 6144;
constexpr int NMAIN = 128, NHELP = 4, NFFN = 112;
constexpr int NSLOT = 4, SLOT_BYTES = 32768, UNIT = 16384, GST_BYTES = 3 * UNIT;
constexpr uint32_t XT0 = 0x9630, XT1 = 0x54DC, XT2 = 0xDC96;
constexpr uint32_t WT0 = 0xA741, WT1 = 0x720A, WT2 = 0x20A7;
constexpr uint32_t AT0 = 0x7420, AT1 = 0x2C0A;
constexpr uint32_t QT = 0x549696DC;
constexpr int OFF_STAGE = 12 * UNIT;
constexpr uint32_t FT_G = 0xB876, FT_U = 0xA931, FT_D = 0x2D0C;
constexpr int OFF_RES = 4 * UNIT;
constexpr int OFF_PAR = 14 * UNIT;
constexpr int OFF_BAR = OFF_PAR + 2048 + 512;
constexpr int SMEM_BYTES = OFF_BAR + 512;
static_assert(SMEM_BYTES <= 232448, "smem");

constexpr int PAR_T1 = 0;
constexpr int PAR_T2 = 1024;
constexpr int PAR_CONST = 1536;
constexpr int PAR_RED = 1600;
constexpr int PAR_SINK = 2176;

struct Maps {
  CUtensorMap x, wq, k, v, wo, wg, wu, wd, wm, out;
};
struct Ptrs {
  const __nv_bfloat16 *x, *w_r, *c, *w_mod, *w_gate, *w_up, *w_down;
  __nv_bfloat16* out;
};

__device__ __align__(1024) uint8_t g_act[16 * 80 * UNIT];
__device__ __align__(128) uint32_t g_mod[NMOD];
__device__ __align__(128) uint32_t g_modp[2 * 2 * DM];
__device__ __align__(128) uint32_t g_ln1[SEQ * 4];
__device__ __align__(128) uint32_t g_cnt_h[16 * 32];
__device__ __align__(128) uint32_t g_cnt_o[128 * 32];
__device__ __align__(128) uint32_t g_xch[NMAIN * 8 * 256 * 4];
__device__ __align__(128) uint32_t g_stats[8 * SEQ * 4];
__device__ __align__(128) uint32_t g_cand[NMAIN * 32];
__device__ __align__(128) uint32_t g_row[16 * 2 * DM];
__device__ __align__(128) uint32_t g_ypart[NMAIN * NFFN * 8];
__device__ uint32_t g_epoch;

__device__ __forceinline__ uint32_t fresh_lane() { uint32_t l; asm volatile("mov.u32 %0, %%laneid;" : "=r"(l)); return l; }
__device__ __forceinline__ uint32_t frag_offset(int warp) {
  const uint32_t l = fresh_lane();
  return ((warp & 3) * 16 + (l & 15)) * 128 + (((l >> 4) ^ (l & 7)) << 4);
}
__device__ __forceinline__ bool elect_one() {
  uint32_t p;
  asm volatile("{ .reg .pred q; elect.sync _|q, 0xffffffff; selp.u32 %0, 1, 0, q; }" : "=r"(p));
  return p;
}
__device__ __forceinline__ uint32_t smem_u32(const void* p) { return (uint32_t)__cvta_generic_to_shared(p); }
__device__ __forceinline__ void mbar_init(uint32_t bar, uint32_t cnt) {
  asm volatile("mbarrier.init.shared::cta.b64 [%0], %1;" ::"r"(bar), "r"(cnt) : "memory");
}
__device__ __forceinline__ void mbar_expect_tx(uint32_t bar, uint32_t bytes) {
  asm volatile("mbarrier.arrive.expect_tx.shared::cta.b64 _, [%0], %1;" ::"r"(bar), "r"(bytes) : "memory");
}
__device__ __forceinline__ void mbar_arrive(uint32_t bar) {
  asm volatile("mbarrier.arrive.shared::cta.b64 _, [%0];" ::"r"(bar) : "memory");
}
__device__ __forceinline__ void mbar_arrive_pred(uint32_t bar, bool p) {
  asm volatile("{ .reg .pred p; setp.ne.b32 p, %1, 0; @p mbarrier.arrive.shared::cta.b64 _, [%0]; }" ::"r"(bar), "r"((int)p) : "memory");
}
__device__ __forceinline__ void mbar_arrive_cl(uint32_t bar, uint32_t off, bool p = true) {
  asm volatile("{ .reg .pred p, q; .reg .b32 a; setp.ne.b32 q, %2, 0; setp.ne.and.b32 p, %0, 0, q; add.u32 a, %0, %1; @p mbarrier.arrive.shared::cluster.b64 _, [a]; }"
               ::"r"(bar), "r"(off), "r"((int)p) : "memory");
}
__device__ __forceinline__ uint32_t mapa(uint32_t addr, uint32_t cta) {
  uint32_t r; asm("mapa.shared::cluster.u32 %0, %1, %2;" : "=r"(r) : "r"(addr), "r"(cta)); return r;
}
__device__ __forceinline__ void cluster_arrive() { asm volatile("barrier.cluster.arrive.relaxed.aligned;" ::: "memory"); }
__device__ __forceinline__ void cluster_wait() { asm volatile("barrier.cluster.wait.aligned;" ::: "memory"); }
__device__ __forceinline__ void watchdog(uint32_t& n) {
}
__device__ __forceinline__ void mbar_wait(uint32_t bar, uint32_t parity) {
  asm volatile("{\n.reg .pred p;\nWAIT_%=:\nmbarrier.try_wait.parity.shared::cta.b64 p, [%0], %1;\n@!p bra WAIT_%=;\n}" ::"r"(bar), "r"(parity) : "memory");
}
__device__ __forceinline__ bool mbar_test(uint32_t bar, uint32_t parity) {
  uint32_t ok;
  asm volatile("{\n.reg .pred p;\nmbarrier.test_wait.parity.shared::cta.b64 p, [%1], %2;\nselp.u32 %0, 1, 0, p;\n}" : "=r"(ok) : "r"(bar), "r"(parity) : "memory");
  return ok;
}
__device__ __forceinline__ uint64_t l2_stream() {
  uint64_t f; asm("createpolicy.fractional.L2::evict_first.b64 %0, 1.0;" : "=l"(f)); return f;
}
__device__ __forceinline__ void tma2d(uint32_t dst, const CUtensorMap* m, int c0, int c1, uint32_t bar) {
  asm volatile("cp.async.bulk.tensor.2d.shared::cluster.global.mbarrier::complete_tx::bytes.L2::cache_hint [%0], [%1, {%3, %4}], [%2], %5;"
               ::"r"(dst), "l"(m), "r"(bar), "r"(c0), "r"(c1), "l"(l2_stream()) : "memory");
}
__device__ __forceinline__ void tma3d_prefetch(const CUtensorMap* m, int c0, int c1, int c2) {
  asm volatile("cp.async.bulk.prefetch.tensor.3d.L2.global.tile [%0, {%1, %2, %3}];" ::"l"(m), "r"(c0), "r"(c1), "r"(c2) : "memory");
}
__device__ __forceinline__ void bulk_load(uint32_t dst, const void* src, uint32_t bytes, uint32_t bar) {
  asm volatile("cp.async.bulk.shared::cluster.global.mbarrier::complete_tx::bytes [%0], [%1], %2, [%3];" ::"r"(dst), "l"(src), "r"(bytes), "r"(bar) : "memory");
}
__device__ __forceinline__ void bulk_load_stream(uint32_t dst, const void* src, uint32_t bytes, uint32_t bar) {
  asm volatile("cp.async.bulk.shared::cluster.global.mbarrier::complete_tx::bytes.L2::cache_hint [%0], [%1], %2, [%3], %4;"
               ::"r"(dst), "l"(src), "r"(bytes), "r"(bar), "l"(l2_stream()) : "memory");
}
__device__ __forceinline__ void tma2d_store(const CUtensorMap* m, uint32_t src, int c0, int c1) {
  asm volatile("cp.async.bulk.tensor.2d.global.shared::cta.bulk_group [%0, {%2, %3}], [%1];" ::"l"(m), "r"(src), "r"(c0), "r"(c1) : "memory");
}
__device__ __forceinline__ void bulk_store(void* dst, uint32_t src, uint32_t bytes) {
  asm volatile("cp.async.bulk.global.shared::cta.bulk_group [%0], [%1], %2;" ::"l"(dst), "r"(src), "r"(bytes) : "memory");
}
__device__ __forceinline__ uint32_t unit_of(uint32_t table, uint32_t i) { return ((table >> (i * 4)) & 15) * UNIT; }
__device__ __forceinline__ void tma3d(uint32_t dst, const CUtensorMap* m, int c0, int c1, int c2, uint32_t bar) {
  asm volatile("cp.async.bulk.tensor.3d.shared::cluster.global.mbarrier::complete_tx::bytes.L2::cache_hint [%0], [%1, {%3, %4, %5}], [%2], %6;"
               ::"r"(dst), "l"(m), "r"(bar), "r"(c0), "r"(c1), "r"(c2), "l"(l2_stream()) : "memory");
}
template <bool STREAM>
__device__ __forceinline__ void tma3d_mc(uint32_t dst, const CUtensorMap* m, int c0, int c1, int c2, uint32_t bar) {
  if (STREAM)
    asm volatile("cp.async.bulk.tensor.3d.shared::cluster.global.mbarrier::complete_tx::bytes.multicast::cluster.L2::cache_hint [%0], [%1, {%3, %4, %5}], [%2], %6, %7;"
                 ::"r"(dst), "l"(m), "r"(bar), "r"(c0), "r"(c1), "r"(c2), "h"((uint16_t)3), "l"(l2_stream()) : "memory");
  else
    asm volatile("cp.async.bulk.tensor.3d.shared::cluster.global.mbarrier::complete_tx::bytes.multicast::cluster [%0], [%1, {%3, %4, %5}], [%2], %6;"
                 ::"r"(dst), "l"(m), "r"(bar), "r"(c0), "r"(c1), "r"(c2), "h"((uint16_t)3) : "memory");
}
__device__ __forceinline__ void prefetch_map(const CUtensorMap* m) {
  asm volatile("prefetch.tensormap [%0];" ::"l"(m) : "memory");
}
__device__ __forceinline__ void fence_async() { asm volatile("fence.proxy.async.global;" ::: "memory"); }
__device__ __forceinline__ void fence_async_smem() { asm volatile("fence.proxy.async.shared::cta;" ::: "memory"); }
__device__ __forceinline__ void bar_sync(int id, int n) { asm volatile("bar.sync %0, %1;" ::"r"(id), "r"(n) : "memory"); }
__device__ __forceinline__ void bar_arrive(int id, int n) { asm volatile("bar.arrive %0, %1;" ::"r"(id), "r"(n) : "memory"); }
__device__ __forceinline__ void wg_fence() { asm volatile("wgmma.fence.sync.aligned;" ::: "memory"); }
__device__ __forceinline__ void wg_commit() { asm volatile("wgmma.commit_group.sync.aligned;" ::: "memory"); }
template <int N> __device__ __forceinline__ void wg_wait() { asm volatile("wgmma.wait_group.sync.aligned %0;" ::"n"(N) : "memory"); }
__device__ __forceinline__ uint64_t make_desc(uint32_t addr, uint32_t lbo, uint32_t sbo) {
  return (uint64_t)((addr & 0x3FFFF) >> 4) | ((uint64_t)(lbo >> 4) << 16) | ((uint64_t)(sbo >> 4) << 32) | (1ull << 62);
}
__device__ __forceinline__ uint32_t ld_relaxed(const uint32_t* p) {
  uint32_t v; asm volatile("ld.relaxed.gpu.global.u32 %0, [%1];" : "=r"(v) : "l"(p) : "memory"); return v;
}
__device__ __forceinline__ uint32_t ld_acquire(const uint32_t* p) {
  uint32_t v; asm volatile("ld.acquire.gpu.global.u32 %0, [%1];" : "=r"(v) : "l"(p) : "memory"); return v;
}
__device__ __forceinline__ uint4 ld_relaxed4(const uint32_t* p) {
  uint4 v; asm volatile("ld.relaxed.gpu.global.v4.u32 {%0,%1,%2,%3}, [%4];" : "=r"(v.x), "=r"(v.y), "=r"(v.z), "=r"(v.w) : "l"(p) : "memory"); return v;
}
__device__ __forceinline__ uint2 ld_relaxed2(const uint32_t* p) {
  uint2 v; asm volatile("ld.relaxed.gpu.global.v2.u32 {%0,%1}, [%2];" : "=r"(v.x), "=r"(v.y) : "l"(p) : "memory"); return v;
}
__device__ __forceinline__ void st_relaxed(uint32_t* p, uint32_t v) {
  asm volatile("st.relaxed.gpu.global.u32 [%0], %1;" ::"l"(p), "r"(v) : "memory");
}
__device__ __forceinline__ void st_relaxed2(uint32_t* p, uint32_t a, uint32_t b) {
  asm volatile("st.relaxed.gpu.global.v2.u32 [%0], {%1,%2};" ::"l"(p), "r"(a), "r"(b) : "memory");
}
__device__ __forceinline__ void st_relaxed4(uint32_t* p, uint32_t a, uint32_t b, uint32_t c, uint32_t d) {
  asm volatile("st.relaxed.gpu.global.v4.u32 [%0], {%1,%2,%3,%4};" ::"l"(p), "r"(a), "r"(b), "r"(c), "r"(d) : "memory");
}
__device__ __forceinline__ void st_b128(uint32_t* p, uint32_t a, uint32_t b, uint32_t c, uint32_t d) {
  asm volatile("{ .reg .b64 u, v; .reg .b128 w; mov.b64 u, {%1, %2}; mov.b64 v, {%3, %4}; mov.b128 w, {u, v}; st.relaxed.gpu.global.b128 [%0], w; }"
               ::"l"(p), "r"(a), "r"(b), "r"(c), "r"(d) : "memory");
}
__device__ __forceinline__ uint4 ld_b128(const uint32_t* p) {
  uint4 r;
  asm volatile("{ .reg .b64 u, v; .reg .b128 w; ld.relaxed.gpu.global.b128 w, [%4]; mov.b128 {u, v}, w; mov.b64 {%0, %1}, u; mov.b64 {%2, %3}, v; }"
               : "=r"(r.x), "=r"(r.y), "=r"(r.z), "=r"(r.w) : "l"(p) : "memory");
  return r;
}
__device__ __forceinline__ void st_pairs(uint32_t* p, uint32_t a, uint32_t b, uint32_t tag) {
  asm volatile("{ .reg .b64 u, v; mov.b64 u, {%1, %3}; mov.b64 v, {%2, %3}; st.relaxed.gpu.global.v2.b64 [%0], {u, v}; }"
               ::"l"(p), "r"(a), "r"(b), "r"(tag) : "memory");
}
__device__ __forceinline__ uint4 ld_pairs(const uint32_t* p) {
  uint4 v;
  asm volatile("{ .reg .b64 u, v; ld.relaxed.gpu.global.v2.b64 {u, v}, [%4]; mov.b64 {%0, %1}, u; mov.b64 {%2, %3}, v; }"
               : "=r"(v.x), "=r"(v.y), "=r"(v.z), "=r"(v.w) : "l"(p) : "memory");
  return v;
}
__device__ __forceinline__ uint2 ld_pair(const uint32_t* p) {
  uint2 v;
  asm volatile("{ .reg .b64 u; ld.relaxed.gpu.global.b64 u, [%2]; mov.b64 {%0, %1}, u; }" : "=r"(v.x), "=r"(v.y) : "l"(p) : "memory");
  return v;
}
__device__ __forceinline__ void red_release(uint32_t* p, uint32_t v) {
  asm volatile("red.release.gpu.global.add.u32 [%0], %1;" ::"l"(p), "r"(v) : "memory");
}
__device__ __forceinline__ uint32_t ldg_nc1(const void* p) {
  uint32_t v;
  asm volatile("ld.global.nc.u32 %0, [%1];" : "=r"(v) : "l"(p));
  return v;
}
__device__ __forceinline__ uint4 ldg_nc4(const void* p) {
  uint4 v; asm volatile("ld.global.nc.L1::no_allocate.v4.u32 {%0,%1,%2,%3}, [%4];" : "=r"(v.x), "=r"(v.y), "=r"(v.z), "=r"(v.w) : "l"(p)); return v;
}
__device__ __forceinline__ void stg4(void* p, uint4 v) {
  asm volatile("st.global.v4.u32 [%0], {%1,%2,%3,%4};" ::"l"(p), "r"(v.x), "r"(v.y), "r"(v.z), "r"(v.w) : "memory");
}
__device__ __forceinline__ void wait_counter(const uint32_t* p, uint32_t target) {
  uint32_t n = 0;
  while ((int)(ld_acquire(p) - target) < 0) { watchdog(n); }
}
__device__ __forceinline__ uint32_t tagf(float v, uint32_t tag) { return (__float_as_uint(v) & ~3u) | tag; }
__device__ __forceinline__ bool tag_ok(uint4 v, uint32_t tag) { return (((v.x ^ tag) | (v.y ^ tag) | (v.z ^ tag) | (v.w ^ tag)) & 3u) == 0; }
__device__ __forceinline__ float untag_sum(uint32_t a, uint32_t b) { return __uint_as_float(a & ~3u) + __uint_as_float(b & ~3u); }
__device__ __forceinline__ uint4 poll4(const uint32_t* p, uint32_t tag) {
  uint4 v = ld_relaxed4(p);
  uint32_t n = 0;
  while (!tag_ok(v, tag)) { v = ld_relaxed4(p); watchdog(n); }
  return v;
}
__device__ __forceinline__ float bf_lo(uint32_t v) { return __uint_as_float(v << 16); }
__device__ __forceinline__ float bf_hi(uint32_t v) { return __uint_as_float(v & 0xffff0000u); }
__device__ __forceinline__ uint32_t pack_bf(float lo, float hi) {
  uint32_t r; asm("cvt.rn.bf16x2.f32 %0, %1, %2;" : "=r"(r) : "f"(hi), "f"(lo)); return r;
}
__device__ __forceinline__ float rbf(float v) { return __uint_as_float(pack_bf(0.f, v) & 0xffff0000u); }
__device__ __forceinline__ uint32_t hmul2(uint32_t a, uint32_t b) {
  uint32_t r; asm("mul.rn.bf16x2 %0, %1, %2;" : "=r"(r) : "r"(a), "r"(b)); return r;
}
__device__ __forceinline__ uint32_t hadd2(uint32_t a, uint32_t b) {
  uint32_t r; asm("add.rn.bf16x2 %0, %1, %2;" : "=r"(r) : "r"(a), "r"(b)); return r;
}
__device__ __forceinline__ uint32_t hsub2(uint32_t a, uint32_t b) {
  uint32_t r; asm("sub.rn.bf16x2 %0, %1, %2;" : "=r"(r) : "r"(a), "r"(b)); return r;
}
__device__ __forceinline__ uint32_t hmax2(uint32_t a, uint32_t b) {
  uint32_t r; asm("max.bf16x2 %0, %1, %2;" : "=r"(r) : "r"(a), "r"(b)); return r;
}
__device__ __forceinline__ float ex2(float x) { float r; asm("ex2.approx.ftz.f32 %0, %1;" : "=f"(r) : "f"(x)); return r; }
__device__ __forceinline__ void stmatrix4(uint32_t addr, uint32_t a, uint32_t b, uint32_t c, uint32_t d) {
  asm volatile("stmatrix.sync.aligned.m8n8.x4.shared.b16 [%0], {%1,%2,%3,%4};" ::"r"(addr), "r"(a), "r"(b), "r"(c), "r"(d) : "memory");
}
__device__ __forceinline__ void ldmatrix4(uint32_t addr, uint32_t& a, uint32_t& b, uint32_t& c, uint32_t& d) {
  asm volatile("ldmatrix.sync.aligned.m8n8.x4.shared.b16 {%0,%1,%2,%3}, [%4];" : "=r"(a), "=r"(b), "=r"(c), "=r"(d) : "r"(addr) : "memory");
}
__device__ __forceinline__ void ldmatrix4t(uint32_t addr, uint32_t& a, uint32_t& b, uint32_t& c, uint32_t& d) {
  asm volatile("ldmatrix.sync.aligned.m8n8.x4.trans.shared.b16 {%0,%1,%2,%3}, [%4];" : "=r"(a), "=r"(b), "=r"(c), "=r"(d) : "r"(addr) : "memory");
}
__device__ __forceinline__ void mma16816(float (&d)[4], uint32_t a0, uint32_t a1, uint32_t a2, uint32_t a3, uint32_t b0, uint32_t b1) {
  asm volatile("mma.sync.aligned.m16n8k16.row.col.f32.bf16.bf16.f32 {%0,%1,%2,%3}, {%4,%5,%6,%7}, {%8,%9}, {%0,%1,%2,%3};"
               : "+f"(d[0]), "+f"(d[1]), "+f"(d[2]), "+f"(d[3]) : "r"(a0), "r"(a1), "r"(a2), "r"(a3), "r"(b0), "r"(b1));
}
__device__ __forceinline__ void sts1(uint32_t a, uint32_t v) { asm volatile("st.shared.u32 [%0], %1;" ::"r"(a), "r"(v) : "memory"); }
__device__ __forceinline__ uint4 lds4(uint32_t a) {
  uint4 v; asm volatile("ld.shared.v4.u32 {%0,%1,%2,%3}, [%4];" : "=r"(v.x), "=r"(v.y), "=r"(v.z), "=r"(v.w) : "r"(a) : "memory"); return v;
}
__device__ __forceinline__ uint2 lds2(uint32_t a) {
  uint2 v; asm volatile("ld.shared.v2.u32 {%0,%1}, [%2];" : "=r"(v.x), "=r"(v.y) : "r"(a) : "memory"); return v;
}
__device__ __forceinline__ uint32_t lds1(uint32_t a) {
  uint32_t v; asm volatile("ld.shared.u32 %0, [%1];" : "=r"(v) : "r"(a) : "memory"); return v;
}
__device__ __forceinline__ void sts2(uint32_t a, uint32_t x, uint32_t y) { asm volatile("st.shared.v2.u32 [%0], {%1,%2};" ::"r"(a), "r"(x), "r"(y) : "memory"); }
__device__ __forceinline__ void sts4(uint32_t a, uint4 v) {
  asm volatile("st.shared.v4.u32 [%0], {%1,%2,%3,%4};" ::"r"(a), "r"(v.x), "r"(v.y), "r"(v.z), "r"(v.w) : "memory");
}
__device__ __forceinline__ float silu_f(float v) { return __fdividef(v, 1.f + __expf(-v)); }
__device__ __forceinline__ uint32_t hfma2(uint32_t a, uint32_t b, uint32_t c) {
  uint32_t r; asm("fma.rn.bf16x2 %0, %1, %2, %3;" : "=r"(r) : "r"(a), "r"(b), "r"(c)); return r;
}
__device__ __forceinline__ void split_inv(float sd, uint32_t& ih, uint32_t& il) {
  const float inv = 1.f / sd;
  ih = pack_bf(inv, inv);
  const float lo = inv - bf_lo(ih);
  il = pack_bf(lo, lo);
}
__device__ __forceinline__ uint32_t ln_mod(uint32_t x, uint32_t mean2, uint32_t ih, uint32_t il, uint32_t c1, uint32_t sh) {
  const uint32_t d = hsub2(x, mean2);
  return hadd2(hmul2(hfma2(d, ih, hmul2(d, il)), c1), sh);
}

#define R8(a, i) "+f"(a[i]), "+f"(a[i + 1]), "+f"(a[i + 2]), "+f"(a[i + 3]), "+f"(a[i + 4]), "+f"(a[i + 5]), "+f"(a[i + 6]), "+f"(a[i + 7])
#define D64 "{%0,%1,%2,%3,%4,%5,%6,%7,%8,%9,%10,%11,%12,%13,%14,%15,%16,%17,%18,%19,%20,%21,%22,%23,%24,%25,%26,%27,%28,%29,%30,%31," \
            "%32,%33,%34,%35,%36,%37,%38,%39,%40,%41,%42,%43,%44,%45,%46,%47,%48,%49,%50,%51,%52,%53,%54,%55,%56,%57,%58,%59,%60,%61,%62,%63}"
template <int TB>
__device__ __forceinline__ void mma_ss(float (&d)[64], uint64_t da, uint64_t db, int sc) {
  asm volatile("{\n.reg .pred p;\nsetp.ne.b32 p, %66, 0;\n"
               "wgmma.mma_async.sync.aligned.m64n128k16.f32.bf16.bf16 " D64 ", %64, %65, p, 1, 1, 0, %67;\n}"
               : R8(d, 0), R8(d, 8), R8(d, 16), R8(d, 24), R8(d, 32), R8(d, 40), R8(d, 48), R8(d, 56)
               : "l"(da), "l"(db), "r"(sc), "n"(TB));
}
template <int TB>
__device__ __forceinline__ void mma_rs(float (&d)[64], uint32_t a0, uint32_t a1, uint32_t a2, uint32_t a3, uint64_t db, int sc) {
  asm volatile("{\n.reg .pred p;\nsetp.ne.b32 p, %69, 0;\n"
               "wgmma.mma_async.sync.aligned.m64n128k16.f32.bf16.bf16 " D64 ", {%64,%65,%66,%67}, %68, p, 1, 1, %70;\n}"
               : R8(d, 0), R8(d, 8), R8(d, 16), R8(d, 24), R8(d, 32), R8(d, 40), R8(d, 48), R8(d, 56)
               : "r"(a0), "r"(a1), "r"(a2), "r"(a3), "l"(db), "r"(sc), "n"(TB));
}
#define D128 "{%0,%1,%2,%3,%4,%5,%6,%7,%8,%9,%10,%11,%12,%13,%14,%15,%16,%17,%18,%19,%20,%21,%22,%23,%24,%25,%26,%27,%28,%29,%30,%31," \
             "%32,%33,%34,%35,%36,%37,%38,%39,%40,%41,%42,%43,%44,%45,%46,%47,%48,%49,%50,%51,%52,%53,%54,%55,%56,%57,%58,%59,%60,%61,%62,%63," \
             "%64,%65,%66,%67,%68,%69,%70,%71,%72,%73,%74,%75,%76,%77,%78,%79,%80,%81,%82,%83,%84,%85,%86,%87,%88,%89,%90,%91,%92,%93,%94,%95," \
             "%96,%97,%98,%99,%100,%101,%102,%103,%104,%105,%106,%107,%108,%109,%110,%111,%112,%113,%114,%115,%116,%117,%118,%119,%120,%121,%122,%123,%124,%125,%126,%127}"
#define R128(d, e) R8(d, 0), R8(d, 8), R8(d, 16), R8(d, 24), R8(d, 32), R8(d, 40), R8(d, 48), R8(d, 56), \
                   R8(e, 0), R8(e, 8), R8(e, 16), R8(e, 24), R8(e, 32), R8(e, 40), R8(e, 48), R8(e, 56)
__device__ __forceinline__ void mma256_ss(float (&d)[64], float (&e)[64], uint64_t da, uint64_t db, int sc) {
  asm volatile("{\n.reg .pred p;\nsetp.ne.b32 p, %130, 0;\n"
               "wgmma.mma_async.sync.aligned.m64n256k16.f32.bf16.bf16 " D128 ", %128, %129, p, 1, 1, 0, 1;\n}"
               : R128(d, e) : "l"(da), "l"(db), "r"(sc));
}
__device__ __forceinline__ void mma256_rs(float (&d)[64], float (&e)[64], uint32_t a0, uint32_t a1, uint32_t a2, uint32_t a3, uint64_t db) {
  asm volatile("{\n.reg .pred p;\nsetp.ne.b32 p, 1, 0;\n"
               "wgmma.mma_async.sync.aligned.m64n256k16.f32.bf16.bf16 " D128 ", {%128,%129,%130,%131}, %132, p, 1, 1, 1;\n}"
               : R128(d, e) : "r"(a0), "r"(a1), "r"(a2), "r"(a3), "l"(db));
}
template <int N> __device__ __forceinline__ void keep(float (&a)[N]) {
#pragma unroll
  for (int i = 0; i < N; i++) asm volatile("" : "+f"(a[i])::"memory");
}
template <int N> __device__ __forceinline__ void keep(uint32_t (&a)[N]) {
#pragma unroll
  for (int i = 0; i < N; i++) asm volatile("" : "+r"(a[i])::"memory");
}

#define PROF(grp, cond, idx) do {} while (0)

constexpr float SCL2 = 1.4426950408889634f * 0.08838834764831845f;

__device__ __forceinline__ void pack_p(const float (&s)[64], uint32_t (&p)[32]) {
#pragma unroll
  for (int i = 0; i < 32; i++) p[i] = pack_bf(s[2 * i], s[2 * i + 1]);
}

__device__ __forceinline__ void issue_qk(float (&s)[64], uint32_t q0, uint32_t q1, uint32_t kslot) {
  const uint64_t db = make_desc(kslot, 16, 1024), da0 = make_desc(q0, 16, 1024), da1 = make_desc(q1, 16, 1024);
#pragma unroll
  for (int kk = 0; kk < 8; kk++) mma_ss<0>(s, (kk < 4 ? da0 : da1) + (kk & 3) * 2, db + (kk >> 2) * 1024 + (kk & 3) * 2, kk != 0);
}
__device__ __forceinline__ void issue_pv(float (&o)[64], uint32_t (&p)[32], uint32_t vslot, int acc) {
  uint64_t db = make_desc(vslot, 16384, 1024);
#pragma unroll
  for (int kk = 0; kk < 8; kk++)
    mma_rs<1>(o, p[4 * kk], p[4 * kk + 1], p[4 * kk + 2], p[4 * kk + 3], db + kk * 128, kk == 0 ? acc : 1);
}

template <int H>
__device__ __forceinline__ void store_chunk(const float (&a)[64], uint32_t addr) {
#pragma unroll
  for (int i = 8 * H; i < 8 * H + 8; i += 2)
    stmatrix4(addr ^ ((i & 7) << 4), pack_bf(a[4 * i], a[4 * i + 1]), pack_bf(a[4 * i + 2], a[4 * i + 3]),
              pack_bf(a[4 * i + 4], a[4 * i + 5]), pack_bf(a[4 * i + 6], a[4 * i + 7]));
}
template <int H>
__device__ __forceinline__ void store_chunk(const float (&a)[64], float i0, float i1, uint32_t addr) {
#pragma unroll
  for (int i = 8 * H; i < 8 * H + 8; i += 2)
    stmatrix4(addr ^ ((i & 7) << 4), pack_bf(a[4 * i] * i0, a[4 * i + 1] * i0), pack_bf(a[4 * i + 2] * i1, a[4 * i + 3] * i1),
              pack_bf(a[4 * i + 4] * i0, a[4 * i + 5] * i0), pack_bf(a[4 * i + 6] * i1, a[4 * i + 7] * i1));
}
__device__ __forceinline__ float inv_quad_sum(float l) {
  l += __shfl_xor_sync(0xffffffffu, l, 1);
  l += __shfl_xor_sync(0xffffffffu, l, 2);
  return __fdividef(1.f, l);
}

__device__ __forceinline__ void ln_scalars(float mean, float var, float& mb, float& sd) {
  mb = rbf(mean);
  sd = rbf(sqrtf(rbf(rbf(var) + 1e-5f)));
}

__global__ void __cluster_dims__(2, 1, 1) __launch_bounds__(384, 1) fused_kernel(const __grid_constant__ Maps maps, const Ptrs P) {
  extern __shared__ __align__(1024) uint8_t smem_raw[];
  const uint32_t base = smem_u32(smem_raw);
  const int tid = threadIdx.x, lane = tid & 31;
  const int warp = __shfl_sync(0xffffffffu, tid >> 5, 0);
  const int b = blockIdx.x;
  PROF(15, tid == 0, 0);

  if (b >= NMAIN) {
    float* sc = reinterpret_cast<float*>(smem_raw);
    float* red = sc + DM;
    for (int k = tid; k < DM; k += 384) sc[k] = rbf(silu_f(__bfloat162float(P.c[k])));
    __syncthreads();
    if (tid < 256) {
      const int col = 2048 + (b - NMAIN) * 1024 + (tid & 127) * 8, r0 = (tid >> 7) * 512;
      float acc[8];
#pragma unroll
      for (int e = 0; e < 8; e++) acc[e] = 0.f;
#pragma unroll 1
      for (int r = r0; r < r0 + 512; r += HU) {
        uint4 w[HU];
#pragma unroll
        for (int u = 0; u < HU; u++) w[u] = ldg_nc4(P.w_mod + (size_t)(r + u) * NMOD + col);
#pragma unroll
        for (int u = 0; u < HU; u++) {
          float s = sc[r + u];
          acc[0] += s * bf_lo(w[u].x); acc[1] += s * bf_hi(w[u].x); acc[2] += s * bf_lo(w[u].y); acc[3] += s * bf_hi(w[u].y);
          acc[4] += s * bf_lo(w[u].z); acc[5] += s * bf_hi(w[u].z); acc[6] += s * bf_lo(w[u].w); acc[7] += s * bf_hi(w[u].w);
        }
      }
      if (tid >= 128) {
#pragma unroll
        for (int e = 0; e < 8; e++) red[(tid & 127) * 8 + e] = acc[e];
      }
      const uint32_t tag = ld_relaxed(&g_epoch) % 3 + 1;
      bar_sync(1, 256);
      if (tid < 128) {
        uint32_t o[8];
#pragma unroll
        for (int e = 0; e < 8; e++) o[e] = __float_as_uint(rbf(acc[e] + red[tid * 8 + e])) | tag;
        st_relaxed4(g_mod + col, o[0], o[1], o[2], o[3]);
        st_relaxed4(g_mod + col + 4, o[4], o[5], o[6], o[7]);
      }
    }
    PROF(2, tid == 0, 1);
    return;
  }

  const int rank = b & 1;
  const int rb = ((b >> 4) << 1) | rank, cj = (b >> 1) & 7;
  const uint32_t bfull = base + OFF_BAR, bempty = bfull + NSLOT * 8;
  const uint32_t gfull = bempty + NSLOT * 8, gempty = gfull + 32;
  const uint32_t bar_ofull = gempty + 32;
  const uint32_t bar_ofree = bar_ofull + 16;
  const uint32_t bar_par = bar_ofree + 32;
  const uint32_t bar_mod = bar_par + 8;
  const uint32_t bar_pread = bar_mod + 8;
  const uint32_t bar_xres = bar_pread + 8;
  const uint32_t bar_ring = bar_xres + 8;
  const uint32_t bar_box = bar_ring + 24;
  const uint32_t bar_go = bar_box + 96;
  const uint32_t bar_go2 = bar_go + 16;
  const uint32_t bar_cnt = bar_go + 24;
  const uint32_t xfull = bar_go + 32, xempty = xfull + 32;
  const uint32_t bar_hw = xempty + 32, bar_hx = bar_hw + 8;
  const uint32_t bar_hpub = bar_hx + 16;
  const uint32_t bar_win = bar_hpub + 8;
  const uint32_t bar_res = bar_go + 8;
  const uint32_t stage = base + OFF_STAGE, par = base + OFF_PAR;

  if (warp == 8 && elect_one()) {
    for (int s = 0; s < NSLOT; s++) { mbar_init(bfull + s * 8, 1); mbar_init(bempty + s * 8, 16); }
    for (int s = 0; s < 4; s++) { mbar_init(gfull + s * 8, 1); mbar_init(gempty + s * 8, 16); mbar_init(xfull + s * 8, 1); mbar_init(xempty + s * 8, 8); mbar_init(bar_ofree + s * 8, 1); }
    mbar_init(bar_ofull, 128); mbar_init(bar_ofull + 8, 128);
    mbar_init(bar_par, 64); mbar_init(bar_mod, 256); mbar_init(bar_pread, 8); mbar_init(bar_xres, 1);
    mbar_init(bar_ring, 8); mbar_init(bar_ring + 8, 8); mbar_init(bar_ring + 16, 8);
    mbar_init(bar_go, 1); mbar_init(bar_go2, 1); mbar_init(bar_cnt, 1); mbar_init(bar_hpub, 8); mbar_init(bar_res, 1); mbar_init(bar_win, 1);
    for (int s = 0; s < 12; s++) mbar_init(bar_box + s * 8, 1);
    asm volatile("fence.mbarrier_init.release.cluster;" ::: "memory");
    prefetch_map(&maps.x); prefetch_map(&maps.wq); prefetch_map(&maps.k); prefetch_map(&maps.v);
  }
  if (warp == 9 && elect_one()) {
    mbar_init(bar_hw, 1); mbar_init(bar_hx, 1); mbar_init(bar_hx + 8, 1);
    asm volatile("fence.mbarrier_init.release.cluster;" ::: "memory");
    mbar_expect_tx(bar_hw, 32768);
    mbar_expect_tx(bar_hx, 16384);
    mbar_expect_tx(bar_hx + 8, 16384);
    const __nv_bfloat16* xs = P.x + (size_t)(rb * 128 + cj * 16) * DM;
    bulk_load(base + 2 * GST_BYTES, xs, 16384, bar_hx);
    tma2d(stage, &maps.wm, (b >> 1) * 32, rank * 512, bar_hw);
    tma2d(stage + 16384, &maps.wm, (b >> 1) * 32, rank * 512 + 256, bar_hw);
    bulk_load(base + 3 * GST_BYTES, xs + 8 * DM, 16384, bar_hx + 8);
  }
  cluster_arrive();

  if (warp >= 8) {
    asm volatile("setmaxnreg.dec.sync.aligned.u32 40;");
    if (warp < 10) bar_arrive(1, 320);
    const uint32_t epoch = ld_relaxed(&g_epoch);
    cluster_wait();
    if (warp == 8) {
      const int kvrow = (cj >> 1) * SK + (SK - WIN);
      int wch = cj * 8 + rank * 2;
#pragma unroll 1
      for (int ps = 0; ps < 3; ps++) {
        const CUtensorMap* mw = ps == 2 ? &maps.wo : &maps.wq;
        const uint32_t xt = ps == 1 ? XT1 : XT2, wt = ps == 0 ? WT0 : (ps == 1 ? WT1 : WT2);
        const int nst = ps == 2 ? 32 : 16;
        if (ps) {
          mbar_wait(bar_ofree + (ps - 1) * 16, 0);
          fence_async();
        }
#pragma unroll 1
        for (int i = 0; i < nst; i++) {
          const uint32_t bf = gfull + (i & 3) * 8;
          const int kt = ps == 2 ? (((cj & 1) * 4 + ((i >> 1) & 3)) * 4 + (i >> 3)) * 2 + (i & 1) : (i + (ps ? 0 : b & 14)) & 15;
          const uint32_t wd = base + unit_of(wt, i & 3) + rank * UNIT, xd = base + unit_of(xt, i & 3);
          const uint8_t* xs = g_act + (uint32_t)(rb * 80 + (ps - 1) * 16 + kt) * UNIT;
          if (ps == 0 && i == HD) mbar_wait(bar_mod, 0);
          if (ps && i && i < 4) mbar_wait(bempty + (i == 3 ? 3 : i - 1) * 8, 1);
          mbar_wait(gempty + (i & 3) * 8, ((i >> 2) & 1) ^ 1);
          if (elect_one()) {
            mbar_expect_tx(bf, ps ? GST_BYTES : 2 * UNIT);
            tma3d_mc<true>(wd, mw, 0, kt * 64, wch, bf);
          }
          if (ps) {
            if (i == 16) mbar_wait(bar_cnt, 0);
            if (i == 2) mbar_wait(bempty + 16, 1);
            if (elect_one()) {
              bulk_load_stream(xd, xs, UNIT, bf);
              mbar_arrive_pred(ps == 1 ? bar_go2 : bar_go, i == (ps == 1 ? 15 : GOST - 1));
              mbar_arrive_pred(bar_res, ((1u << RES0 | 1u << RES1) >> i) & 1);
            }
          }
        }
        if (ps == 2) break;
        wch = ps ? ((wch >> 3) ^ rank) * 2 : wch + 4;
#pragma unroll 1
        for (int u = 0; u < 16; u++) {
          const bool isk = (u == 0) || ((u & 1) && u < 15);
          const int blk = (isk ? (u + 1) >> 1 : (u == 15 ? 7 : (u >> 1) - 1)) & 3;
          const uint32_t sl = base + unit_of(ps ? AT1 : AT0, u & 3) + rank * UNIT, bf = bfull + (u & 3) * 8;
          if (u < 4) mbar_wait(gempty + ((u + 1) >> 1) * 8, 1);
          mbar_wait(bempty + (u & 3) * 8, ((u >> 2) & 1) ^ 1);
          if (elect_one()) {
            mbar_expect_tx(bf, SLOT_BYTES);
            tma3d_mc<false>(sl, isk ? &maps.k : &maps.v, 0, kvrow + blk * 128, rank, bf);
          }
        }
      }
      if (b < NFFN) {
#pragma unroll 1
        for (int u = 0; u < 12; u++) {
          if (u == 0 || u == 3 || u == 6) mbar_wait(bar_ring + (u / 3) * 8, 0);
          if (u >= FPACE) mbar_wait(bar_box + (u - FPACE) * 8, 0);
          const uint32_t dst = base + unit_of(u < 4 ? FT_G : (u < 8 ? FT_U : FT_D), u & 3);
          if (elect_one()) {
            mbar_expect_tx(bar_box + u * 8, UNIT);
            if (u < 8) tma2d(dst, u < 4 ? &maps.wg : &maps.wu, b * 32, (u & 3) * 256, bar_box + u * 8);
            else tma3d(dst, &maps.wd, 0, b * 32, (u - 8) * 4, bar_box + u * 8);
          }
        }
      }
    } else if (warp == 9) {
      const uint32_t target = 8 * (epoch + 1);
#pragma unroll 1
      for (int i = 0; i < 16; i++) {
        if (i == HDX) mbar_wait(bar_mod, 0);
        if (i == NRS) {
          wait_counter(&g_cnt_h[rb * 32], target);
          PROF(1, lane == 0, 26);
          fence_async();
        }
        mbar_wait(xempty + (i & 3) * 8, ((i >> 2) & 1) ^ 1);
        if (elect_one()) {
          mbar_expect_tx(xfull + (i & 3) * 8, UNIT);
          if (i < NRS) tma2d(base + (i & 3) * GST_BYTES, &maps.x, ((2 * cj + i) & 15) * 64, rb * 128, xfull + (i & 3) * 8);
          else bulk_load_stream(base + (i & 3) * GST_BYTES, g_act + (uint32_t)(rb * 80 + ((2 * cj + i) & 15)) * UNIT, UNIT, xfull + (i & 3) * 8);
        }
      }
      prefetch_map(&maps.wo);
#pragma unroll 1
      for (int t = 0; t < 4; t++) {
#pragma unroll 1
        for (int w = 0; w < 2; w++) {
          mbar_wait(bar_ofull + w * 8, t & 1);
          uint8_t* dst = g_act + (uint32_t)(rb * 80 + 16 + (cj * 4 + t) * 2) * UNIT + w * 8192;
          if (elect_one()) {
            bulk_store(dst, base + unit_of(QT, 2 * t) + w * 8192, 8192);
            bulk_store(dst + UNIT, base + unit_of(QT, 2 * t + 1) + w * 8192, 8192);
            asm volatile("cp.async.bulk.commit_group;" ::: "memory");
          }
        }
        if (elect_one()) {
          asm volatile("cp.async.bulk.wait_group.read 0;" ::: "memory");
          mbar_arrive(bar_ofree + t * 8);
          asm volatile("cp.async.bulk.wait_group 0;" ::: "memory");
          fence_async();
          red_release(&g_cnt_o[((rb * 4 + t) * 2 + (cj >> 2)) * 32], 2);
          if (t == PF2T) for (int u = 0; u < PF2; u++)
            tma3d_prefetch(&maps.wo, 0, ((((cj & 1) * 4 + (b >> 5)) * 4 + u) * 2 + ((b >> 4) & 1)) * 64, (cj ^ rank) * 2);
        }
        if (t & 1) {
          wait_counter(&g_cnt_o[(rb * 8 + 2 * t - 2 + (cj & 1)) * 32], target);
          wait_counter(&g_cnt_o[(rb * 8 + 2 * t + (cj & 1)) * 32], target);
        }
      }
      fence_async();
      if (elect_one()) {
        mbar_arrive(bar_cnt);
        PROF(2, true, 27);
        mbar_expect_tx(bar_xres, 32768);
      }
#pragma unroll 1
      for (int u = 0; u < 2; u++) {
        mbar_wait(bar_res, u);
        if (elect_one()) tma2d(base + OFF_RES + u * UNIT, &maps.x, cj * 128 + u * 64, rb * 128, bar_xres);
      }
    } else {
      const int t2 = tid - 320;
      if (t2 == 0) {
        mbar_wait(bar_hpub, 0);
        PROF(1, true, 24);
        red_release(&g_cnt_h[rb * 32], 1);
        PROF(1, true, 25);
        prefetch_map(&maps.wg); prefetch_map(&maps.wu); prefetch_map(&maps.wd); prefetch_map(&maps.out);
      }
      __syncwarp();
      if (b < NFFN) {
        mbar_wait(bar_go2, 0);
        const __nv_bfloat16* pg = ((b & 1) ? P.w_up : P.w_gate) + (b >> 1) * 64 + (size_t)t2 * FF;
        const __nv_bfloat16* pd = P.w_down + (size_t)b * 32768 + t2 * 64;
        PROF(2, t2 == 0, 13);
#pragma unroll 1
        for (int i = 0; i < WN; i += WB) {
          uint32_t v[WB];
#pragma unroll
          for (int u = 0; u < WB; u++)
            asm volatile("ld.global.cg.L2::128B.u32 %0, [%1];" : "=r"(v[u]) : "l"(i < 16 ? pg + (size_t)(i + u) * 64 * FF : pd + (i + u - 16) * 4096));
#pragma unroll
          for (int u = 1; u < WB; u++) v[0] ^= v[u];
          sts1(par + PAR_SINK + t2 * 4, v[0]);
        }
        PROF(2, t2 == 0, 14);
      }
      const uint32_t tag = epoch % 3 + 1;
      mbar_wait(bar_cnt, 0);
      float s1 = 0.f, s2 = 0.f;
#pragma unroll 1
      for (int q = 0; q < 4; q++) {
        const int col = q * 256 + t2 * 4;
        uint4 vsb = poll4(g_mod + 3 * DM + col, tag), vcb = poll4(g_mod + 4 * DM + col, tag);
        uint2 wr = *reinterpret_cast<const uint2*>(P.w_r + col);
        float c0 = rbf(1.f + bf_hi(vcb.x)), c1 = rbf(1.f + bf_hi(vcb.y)), c2 = rbf(1.f + bf_hi(vcb.z)), c3 = rbf(1.f + bf_hi(vcb.w));
        float a0 = c0 * bf_lo(wr.x), a1 = c1 * bf_hi(wr.x), a2 = c2 * bf_lo(wr.y), a3 = c3 * bf_hi(wr.y);
        s1 += (a0 + a1) + (a2 + a3);
        s2 += bf_hi(vsb.x) * bf_lo(wr.x) + bf_hi(vsb.y) * bf_hi(wr.x) + bf_hi(vsb.z) * bf_lo(wr.y) + bf_hi(vsb.w) * bf_hi(wr.y);
        if ((col >> 7) == cj) {
          const int lc = col & 127;
          uint4 vga = poll4(g_mod + 2 * DM + col, tag), vgb = poll4(g_mod + 5 * DM + col, tag);
          sts4(par + PAR_T1 + lc * 8, make_uint4(__byte_perm(vga.x, vga.y, 0x7632), __byte_perm(vgb.x, vgb.y, 0x7632), __float_as_uint(a0), __float_as_uint(a1)));
          sts4(par + PAR_T1 + lc * 8 + 16, make_uint4(__byte_perm(vga.z, vga.w, 0x7632), __byte_perm(vgb.z, vgb.w, 0x7632), __float_as_uint(a2), __float_as_uint(a3)));
          sts4(par + PAR_T2 + lc * 4, make_uint4(pack_bf(c0, c1), __byte_perm(vsb.x, vsb.y, 0x7632), pack_bf(c2, c3), __byte_perm(vsb.z, vsb.w, 0x7632)));
        }
      }
#pragma unroll
      for (int o = 16; o > 0; o >>= 1) { s1 += __shfl_xor_sync(0xffffffffu, s1, o); s2 += __shfl_xor_sync(0xffffffffu, s2, o); }
      if (lane == 0) { sts2(par + PAR_CONST + (warp - 10) * 8, __float_as_uint(s1), __float_as_uint(s2)); sts1(par + PAR_CONST + 48, epoch); }
      if (t2 < 2) {
        uint4 g = poll4(g_mod + 5 * DM + b * 8 + t2 * 4, tag);
        sts4(par + PAR_CONST + 16 + t2 * 16, g);
      }
      mbar_wait(bar_go, 0);
#pragma unroll 4
      for (int q = XR; q < XE; q++) st_b128(g_xch + ((size_t)b * 8 * 256 + q * 64 + t2) * 4, (epoch & 1) << 16, 0, 0, 0);
      for (int q = 0; q < 2; q++) st_relaxed4(g_stats + ((size_t)cj * SEQ + rb * 128 + q * 64 + t2) * 4, 0, 0, 0, 0);
      if (b < NFFN)
        for (int q = 0; q < 4; q++) st_relaxed4(g_ypart + ((size_t)(q * 32 + (t2 >> 1)) * NFFN + b) * 8 + (t2 & 1) * 4, 0, 0, 0, 0);
      st_relaxed4(g_row + rb * 2 * DM + (t2 >> 5) * DM + cj * 128 + (t2 & 31) * 4, 0, 0, 0, 0);
      if (t2 < 16) st_relaxed2(g_cand + (cj * 16 + t2) * 32 + rb * 2, 0, 0);
      __threadfence();
      mbar_arrive(bar_par);
    }
    __syncwarp();
    cluster_arrive();
    {
      const uint32_t tag = epoch % 3 + 1, t3 = tid - 256;
      mbar_wait(bar_win, 0);
      const uint2 win = lds2(par + PAR_CONST + 56);
      const uint32_t* fsrc = g_row + (win.y >> 7) * 2 * DM + (b >> 1) * 16 + (t3 & 3) * 4 + (b & 1) * 2;
      const uint32_t* ysrc = g_ypart + ((size_t)b * NFFN + min(t3, NFFN - 1)) * 8;
      uint2 fh = ld_pair(fsrc), fx = ld_pair(fsrc + DM);
      uint4 ya = ld_relaxed4(ysrc), yb = ld_relaxed4(ysrc + 4);
      const float rwin = __uint_as_float(((int)win.x < 0 ? win.x & 0x7fffffffu : ~win.x) & ~3u);
      const float rs = rbf(1.f / (1.f + __expf(-rbf(rwin))));
      uint32_t n = 0;
      while (fh.y != tag || fx.y != tag) { fh = ld_pair(fsrc); fx = ld_pair(fsrc + DM); watchdog(n); }
      while (!(tag_ok(ya, tag) && tag_ok(yb, tag))) { ya = ld_relaxed4(ysrc); yb = ld_relaxed4(ysrc + 4); watchdog(n); }
      __syncwarp();
      PROF(8, t3 == 0, 5);
      const uint32_t msk = t3 < NFFN ? ~3u : 0u;
      float y[8] = {__uint_as_float(ya.x & msk), __uint_as_float(ya.y & msk), __uint_as_float(ya.z & msk), __uint_as_float(ya.w & msk),
                    __uint_as_float(yb.x & msk), __uint_as_float(yb.y & msk), __uint_as_float(yb.z & msk), __uint_as_float(yb.w & msk)};
#pragma unroll
      for (int h = 4; h > 0; h >>= 1) {
        const bool up = lane & (h * 4);
#pragma unroll
        for (int e = 0; e < h; e++) y[e] = (up ? y[e + h] : y[e]) + __shfl_xor_sync(0xffffffffu, up ? y[e] : y[e + h], h * 4);
      }
      y[0] += __shfl_xor_sync(0xffffffffu, y[0], 1);
      y[0] += __shfl_xor_sync(0xffffffffu, y[0], 2);
      if ((lane & 3) == 0) sts1(par + PAR_RED + 64 + t3, __float_as_uint(y[0]));
      bar_sync(4, 128);
      if (t3 < 4) {
        float y0 = 0.f, y1 = 0.f;
#pragma unroll
        for (int w4 = 0; w4 < 4; w4++) {
          const uint2 v = lds2(par + PAR_RED + 64 + w4 * 32 + t3 * 8);
          y0 += __uint_as_float(v.x); y1 += __uint_as_float(v.y);
        }
        const uint2 gv = lds2(par + PAR_CONST + 16 + t3 * 8);
        const uint32_t upd = hmul2(pack_bf(y0, y1), pack_bf(rs, rs));
        *reinterpret_cast<uint32_t*>(P.out + (size_t)win.y * DM + b * 8 + t3 * 2) =
            hadd2(fx.x, hmul2(__byte_perm(gv.x, gv.y, 0x7632), hadd2(fh.x, upd)));
        if (b == 0 && t3 == 0) st_relaxed(&g_epoch, epoch + 1);
      }
      PROF(15, t3 == 0, 36);
    }
    cluster_wait();
  } else {
    const int wg = warp >> 2;

    uint32_t tag;
    {
      uint32_t* const pmod = g_modp + rank * 2 * DM + (b >> 1) * 32 + lane;
      uint32_t* const pln = g_ln1 + (rb * 128 + cj * 16 + warp) * 4;
      const uint32_t cv = ldg_nc1(P.c + rank * 512 + tid * 2);
      const uint32_t epoch = ld_relaxed(&g_epoch);
      if (warp == 0) st_relaxed(pmod, 0);
      if (lane == 0) { st_relaxed2(pln, 0, 0); st_relaxed2(pln + 32, 0, 0); }
      asm volatile("setmaxnreg.inc.sync.aligned.u32 232;");
      sts1(par + tid * 4, pack_bf(silu_f(bf_lo(cv)), silu_f(bf_hi(cv))));
      bar_sync(1, 320);
      tag = epoch % 3 + 1;
#pragma unroll
      for (int part = 0; part < 3; part++) {
        if (part != 1) {
          const uint32_t xa = base + (2 + part / 2) * GST_BYTES + warp * 2048 + lane * 16;
          mbar_wait(bar_hx + part * 4, 0);
          float s0 = 0.f, s1 = 0.f, q0 = 0.f, q1 = 0.f;
#pragma unroll
          for (int q = 0; q < 4; q++) {
            const uint4 xv = lds4(xa + q * 512);
            const uint32_t u[4] = {xv.x, xv.y, xv.z, xv.w};
#pragma unroll
            for (int e = 0; e < 4; e++) { const float lo = bf_lo(u[e]), hi = bf_hi(u[e]); s0 += lo; s1 += hi; q0 += lo * lo; q1 += hi * hi; }
          }
          s0 += s1; q0 += q1;
#pragma unroll
          for (int o = 16; o > 0; o >>= 1) { s0 += __shfl_xor_sync(0xffffffffu, s0, o); q0 += __shfl_xor_sync(0xffffffffu, q0, o); }
          const float mean = s0 * (1.f / DM);
          float mb, sd;
          ln_scalars(mean, fmaxf(q0 * (1.f / DM) - mean * mean, 0.f), mb, sd);
          if (lane == 0) st_relaxed2(pln + part * 16, __float_as_uint(mb) | tag, __float_as_uint(sd) | tag);
          PROF(1, tid == 0 && part == 2, 4);
        } else {
          float acc[8];
#pragma unroll
          for (int e = 0; e < 8; e++) acc[e] = 0.f;
          const uint32_t wa = stage + (tid >> 2) * 64 + (((tid ^ (tid >> 3)) & 3) << 4), sa = par + (tid >> 3) * 4, sh = (tid & 4) ? 0x3244 : 0x1044;
          mbar_wait(bar_hw, 0);
#pragma unroll
          for (int p = 0; p < 8; p++) {
            const uint4 w = lds4(wa + p * 4096);
            const float s = __uint_as_float(__byte_perm(lds1(sa + p * 128), 0, sh));
            acc[0] += s * bf_lo(w.x); acc[1] += s * bf_hi(w.x); acc[2] += s * bf_lo(w.y); acc[3] += s * bf_hi(w.y);
            acc[4] += s * bf_lo(w.z); acc[5] += s * bf_hi(w.z); acc[6] += s * bf_lo(w.w); acc[7] += s * bf_hi(w.w);
          }
#pragma unroll
          for (int e = 0; e < 4; e++) {
            const bool up = lane & 16;
            acc[e] = (up ? acc[e + 4] : acc[e]) + __shfl_xor_sync(0xffffffffu, up ? acc[e] : acc[e + 4], 16);
          }
#pragma unroll
          for (int e = 0; e < 2; e++) {
            const bool up = lane & 8;
            acc[e] = (up ? acc[e + 2] : acc[e]) + __shfl_xor_sync(0xffffffffu, up ? acc[e] : acc[e + 2], 8);
          }
          {
            const bool up = lane & 4;
            acc[0] = (up ? acc[1] : acc[0]) + __shfl_xor_sync(0xffffffffu, up ? acc[0] : acc[1], 4);
          }
          sts1(par + 1024 + warp * 128 + ((lane & 3) * 8 + (lane >> 2)) * 4, __float_as_uint(acc[0]));
          bar_sync(1, 256);
          if (warp == 0) {
            float s = 0.f;
#pragma unroll
            for (int w8 = 0; w8 < 8; w8++) s += __uint_as_float(lds1(par + 1024 + w8 * 128 + lane * 4));
            st_relaxed(pmod, (__float_as_uint(s) & ~3u) | tag);
          }
          PROF(1, tid == 0, 3);
        }
      }
      {
        uint2 s0 = ld_relaxed2(g_ln1 + (rb * 128 + (tid & 127)) * 4);
        uint4 v[4];
#pragma unroll
        for (int q = 0; q < 4; q++) v[q] = ld_relaxed4(g_modp + q * DM + tid * 4);
        {
          uint32_t n = 0;
          while (!(tag_ok(v[0], tag) && tag_ok(v[1], tag) && tag_ok(v[2], tag) && tag_ok(v[3], tag))) {
#pragma unroll
            for (int q = 0; q < 4; q++)
              if (!tag_ok(v[q], tag)) v[q] = ld_relaxed4(g_modp + q * DM + tid * 4);
            if (((s0.x ^ tag) | (s0.y ^ tag)) & 3u) s0 = ld_relaxed2(g_ln1 + (rb * 128 + (tid & 127)) * 4);
            watchdog(n);
          }
        }
        const uint32_t d = stage + (tid >> 2) * 64 + (tid & 1) * 32 + (tid & 2) * 2;
        sts1(d, pack_bf(1.f + rbf(untag_sum(v[1].x, v[3].x)), 1.f + rbf(untag_sum(v[1].y, v[3].y))));
        sts1(d + 16, pack_bf(1.f + rbf(untag_sum(v[1].z, v[3].z)), 1.f + rbf(untag_sum(v[1].w, v[3].w))));
        sts1(d + 8, pack_bf(untag_sum(v[0].x, v[2].x), untag_sum(v[0].y, v[2].y)));
        sts1(d + 24, pack_bf(untag_sum(v[0].z, v[2].z), untag_sum(v[0].w, v[2].w)));
        if (wg == 0) {
          uint32_t n = 0;
          while (((s0.x ^ tag) | (s0.y ^ tag)) & 3u) { s0 = ld_relaxed2(g_ln1 + (rb * 128 + tid) * 4); watchdog(n); }
          uint32_t ih, il;
          split_inv(bf_hi(s0.y), ih, il);
          sts4(stage + 4096 + tid * 16, make_uint4(__byte_perm(s0.x, 0, 0x3232), ih, il, 0));
        }
        mbar_arrive(bar_mod);
      }
      cluster_wait();
      if (wg == 1) bar_arrive(2, 256);
      mbar_wait(bar_mod, 0);
      PROF(1, tid == 0, 2);
    }

    float f0 = 0.f, f1 = 0.f;
    const uint32_t rempty = lane < 2 ? mapa(bempty, lane & 1) : 0;
    constexpr uint32_t GE = NSLOT * 8 + 32;
    float o[64], s[64];
#pragma unroll 1
    for (int ps = 0; ps < 3; ps++) {
      {
        const uint32_t xt = ps == 1 ? XT1 : XT2, wt = ps == 1 ? WT1 : WT2;
        const int nst = ps == 2 ? 29 : 14;
        if (ps == 0) {
          float ga[64], gb[64];
#pragma unroll
          for (int i = 0; i < 64; i++) { ga[i] = 0.f; gb[i] = 0.f; }
          uint32_t a[2][16];
          const uint32_t l = fresh_lane();
          const uint4 r0 = lds4(stage + 4096 + (warp * 16 + (l >> 2)) * 16), r1 = lds4(stage + 4096 + 128 + (warp * 16 + (l >> 2)) * 16);
          auto transform = [&](int i, uint32_t (&f)[16], uint32_t z) {
            const uint32_t ad = base + (i & 3) * GST_BYTES + wg * 8192 + frag_offset(warp) + z;
            mbar_wait(xfull + (i & 3) * 8, i >> 2);
#pragma unroll
            for (int kk = 0; kk < 4; kk++) ldmatrix4(ad ^ (kk * 32), f[4 * kk], f[4 * kk + 1], f[4 * kk + 2], f[4 * kk + 3]);
#pragma unroll
            for (int kk = 0; kk < 4; kk++) {
              const uint4 m = lds4(stage + (l & 3) * 16 + ((2 * cj + i) & 15) * 256 + kk * 64);
              f[4 * kk] = ln_mod(f[4 * kk], r0.x, r0.y, r0.z, m.x, m.z);
              f[4 * kk + 1] = ln_mod(f[4 * kk + 1], r1.x, r1.y, r1.z, m.x, m.z);
              f[4 * kk + 2] = ln_mod(f[4 * kk + 2], r0.x, r0.y, r0.z, m.y, m.w);
              f[4 * kk + 3] = ln_mod(f[4 * kk + 3], r1.x, r1.y, r1.z, m.y, m.w);
            }
            keep(f);
            mbar_arrive_pred(xempty + (i & 3) * 8, l == 0);
          };
          auto publish = [&](int u, uint32_t (&f)[16]) {
            const uint32_t sc = stage + 8192 + wg * 8192;
#pragma unroll
            for (int kk = 0; kk < 4; kk++) stmatrix4((sc + frag_offset(warp)) ^ (kk * 32), f[4 * kk], f[4 * kk + 1], f[4 * kk + 2], f[4 * kk + 3]);
            __syncwarp();
            const uint32_t src = sc + (warp & 3) * 2048 + l * 16;
            uint8_t* dst = g_act + (uint32_t)(rb * 80 + cj * 2 + u) * UNIT + warp * 2048 + l * 16;
#pragma unroll
            for (int p4 = 0; p4 < 4; p4++) stg4(dst + p4 * 512, lds4(src + p4 * 512));
            __syncwarp();
            if (u == 1) mbar_arrive_pred(bar_hpub, l == 0);
          };
          auto multiply = [&](int i, uint32_t (&f)[16]) {
            mbar_wait(gfull + (i & 3) * 8, i >> 2);
            const uint64_t db = make_desc(base + (i & 3) * GST_BYTES + UNIT, 8192, 1024);
            wg_fence();
#pragma unroll
            for (int kk = 0; kk < 4; kk++) mma256_rs(ga, gb, f[4 * kk], f[4 * kk + 1], f[4 * kk + 2], f[4 * kk + 3], db + kk * 128);
            wg_commit();
          };
          transform(0, a[0], 0); publish(0, a[0]); transform(1, a[1], 0); multiply(0, a[0]); publish(1, a[1]);
#pragma unroll
          for (int i = 1; i < NRS; i++) {
            if (i >= 2) {
              uint32_t z = r0.w;
#pragma unroll
              for (int k = 0; k < 16; k += 2) asm volatile("lop3.b32 %0, %1, %2, %0, 0xA8;" : "+r"(z) : "r"(a[i & 1][k]), "r"(a[i & 1][k + 1]));
              transform(i, a[i & 1], z);
            }
            multiply(i, a[i & 1]);
            wg_wait<1>();
            mbar_arrive_cl(rempty, GE + ((i + 3) & 3) * 8);
          }
          mbar_arrive_pred(bar_pread, l == 0);
#pragma unroll 1
          for (int i = NRS; i < 14; i++) {
            mbar_wait(xfull + (i & 3) * 8, (i >> 2) & 1);
            mbar_wait(gfull + (i & 3) * 8, (i >> 2) & 1);
            const uint32_t xa = base + (i & 3) * GST_BYTES;
            const uint64_t da = make_desc(xa + wg * 8192, 16, 1024), db = make_desc(xa + UNIT, 8192, 1024);
            if (i == 13) bar_sync(2 + wg, 256);
            wg_fence();
#pragma unroll
            for (int kk = 0; kk < 4; kk++) mma256_ss(ga, gb, da + kk * 2, db + kk * 128, 1);
            wg_commit();
            if (i == 13) bar_arrive(3 - wg, 256);
            wg_wait<1>();
            uint32_t z = r0.w;
#pragma unroll
            for (int k = 0; k < 16; k += 2) asm volatile("lop3.b32 %0, %1, %2, %0, 0xA8;" : "+r"(z) : "r"(a[1][k]), "r"(a[1][k + 1]));
            mbar_arrive_cl(rempty, GE + ((i + 3) & 3) * 8 + z);
            mbar_arrive_pred(xempty + ((i + 3) & 3) * 8, l == 0 && i != NRS);
          }
          mbar_wait(xfull + 16, 1);
          mbar_wait(xfull + 24, 1);
          wg_wait<0>();
          keep(ga); keep(gb);
#pragma unroll
          for (int i = 0; i < 64; i++) {
            asm volatile("mov.b32 %0, %1;" : "=f"(s[i]) : "f"(ga[i]));
            asm volatile("mov.b32 %0, %1;" : "=f"(o[i]) : "f"(gb[i]));
          }
        } else {
          float ga[64], gb[64];
#pragma unroll
          for (int i = 0; i < 64; i++) {
            asm volatile("mov.b32 %0, %1;" : "=f"(ga[i]) : "f"(s[i]));
            asm volatile("mov.b32 %0, %1;" : "=f"(gb[i]) : "f"(o[i]));
          }
#pragma unroll 1
          for (int i = 0; i < nst; i++) {
            mbar_wait(gfull + (i & 3) * 8, (i >> 2) & 1);
            const uint64_t da = make_desc(base + unit_of(xt, i & 3) + wg * 8192, 16, 1024), db = make_desc(base + unit_of(wt, i & 3), 8192, 1024);
            if (i == nst - 1) bar_sync(2 + wg, 256);
            wg_fence();
#pragma unroll
            for (int kk = 0; kk < 4; kk++) mma256_ss(ga, gb, da + kk * 2, db + kk * 128, kk ? 1 : i);
            wg_commit();
            if (i == nst - 1) bar_arrive(3 - wg, 256);
            wg_wait<1>();
            mbar_arrive_cl(rempty, GE + ((i + 3) & 3) * 8, i != 0);
            PROF(4, tid == 0 && (i & 3) == 0, 40 + (ps - 1) * 4 + i / 4);
          }
          wg_wait<0>();
          keep(ga); keep(gb);
#pragma unroll
          for (int i = 0; i < 64; i++) {
            asm volatile("mov.b32 %0, %1;" : "=f"(s[i]) : "f"(ga[i]));
            asm volatile("mov.b32 %0, %1;" : "=f"(o[i]) : "f"(gb[i]));
          }
        }
        if (ps == 2) break;
        mbar_arrive_cl(rempty, GE + 8);
      }
      const uint32_t qw = base + wg * 8192, qt = QT >> (16 * ps), at = ps ? AT1 : AT0;
      {
        const uint32_t wt = ps ? WT1 : WT0;
        const uint64_t da0 = make_desc(qw + unit_of(qt, 2), 16, 1024), da1 = make_desc(qw + unit_of(qt, 3), 16, 1024);
        const uint64_t db0 = make_desc(base + unit_of(wt, 2), 8192, 1024), db1 = make_desc(base + unit_of(wt, 3), 8192, 1024);
        mbar_wait(gfull + 16, 1);
        mbar_wait(gfull + 24, 1);
        bar_sync(2 + wg, 256);
        wg_fence();
#pragma unroll
        for (int kk = 0; kk < 8; kk++) mma_ss<1>(s, (kk < 4 ? da0 : da1) + (kk & 3) * 2, (kk < 4 ? db0 : db1) + (kk & 3) * 128, 1);
        wg_commit();
        bar_arrive(3 - wg, 256);
        mbar_wait(ps == 0 ? bar_pread : bar_ofree + 8, 0);
        mbar_wait(bfull, 0);
        wg_wait<0>();
        keep(s);
        PROF(2, tid == 0, 8 + ps * 8);
        store_chunk<0>(s, qw + unit_of(qt, 0) + frag_offset(warp));
        store_chunk<1>(s, qw + unit_of(qt, 1) + frag_offset(warp));
        fence_async_smem();
        bar_sync(2 + wg, 256);
        wg_fence();
        issue_qk(s, qw + unit_of(qt, 0), qw + unit_of(qt, 1), base + unit_of(at, 0));
        wg_commit();
#pragma unroll
        for (int kk = 0; kk < 8; kk++) mma_ss<1>(o, (kk < 4 ? da0 : da1) + (kk & 3) * 2, (kk < 4 ? db0 : db1) + UNIT / 16 + (kk & 3) * 128, 1);
        wg_commit();
        bar_arrive(3 - wg, 256);
        wg_wait<1>();
        keep(s);
        mbar_arrive_cl(rempty, 0);
      }
      PROF(4, tid == 0 && ps == 1, 61);
      float l0 = 0.25f, l1 = 0.25f;
      auto step = [&](auto odd_c, const int j, uint32_t (&pw)[32], uint32_t (&pr)[32]) {
        constexpr bool ODD = decltype(odd_c)::value;
        const bool first = !ODD && (j & 2) == 0, last = ODD && j == 7;
        const uint32_t ph = (j >> 1) & 1;
        float i0, i1, a0, a1;
        if (first) { i0 = inv_quad_sum(l0); i1 = inv_quad_sum(l1); l0 = 0.f; l1 = 0.f; }
        bool redo = !ODD && (j | ps) == 0, again = false;
        while (true) {
          if (redo) {
            float m0 = fmaxf(s[0], s[1]), m1 = fmaxf(s[2], s[3]);
#pragma unroll
            for (int i = 1; i < 16; i++) { m0 = fmaxf(m0, fmaxf(s[4 * i], s[4 * i + 1])); m1 = fmaxf(m1, fmaxf(s[4 * i + 2], s[4 * i + 3])); }
            m0 = fmaxf(m0, __shfl_xor_sync(0xffffffffu, m0, 1)); m1 = fmaxf(m1, __shfl_xor_sync(0xffffffffu, m1, 1));
            m0 = fmaxf(m0, __shfl_xor_sync(0xffffffffu, m0, 2)); m1 = fmaxf(m1, __shfl_xor_sync(0xffffffffu, m1, 2));
            m0 *= SCL2; m1 *= SCL2;
            if (!first) {
              m0 = fmaxf(m0, f0); m1 = fmaxf(m1, f1);
              const float c0 = ex2(f0 - m0), c1 = ex2(f1 - m1);
              l0 *= c0; l1 *= c1;
              wg_wait<0>();
              keep(o);
#pragma unroll
              for (int i = 0; i < 16; i++) { o[4 * i] *= c0; o[4 * i + 1] *= c0; o[4 * i + 2] *= c1; o[4 * i + 3] *= c1; }
            }
            f0 = m0; f1 = m1;
          }
          float b0 = 0.f, b1 = 0.f;
          a0 = 0.f; a1 = 0.f;
#pragma unroll
          for (int i = 0; i < 16; i++) {
            const float e0 = ex2(fmaf(s[4 * i], SCL2, -f0)), e1 = ex2(fmaf(s[4 * i + 1], SCL2, -f0));
            const float e2 = ex2(fmaf(s[4 * i + 2], SCL2, -f1)), e3 = ex2(fmaf(s[4 * i + 3], SCL2, -f1));
            a0 += e0; b0 += e1; a1 += e2; b1 += e3;
            pw[2 * i] = pack_bf(e0, e1); pw[2 * i + 1] = pack_bf(e2, e3);
            if (i == VREL) {
#pragma unroll
              for (int k = 0; k < 2 * VREL + 2; k++) asm volatile("" : "+r"(pw[k])::"memory");
              mbar_wait(bfull + (ODD ? 24 : 8), ph);
              wg_wait<0>();
              mbar_arrive_cl(rempty, ODD ? 16 : (j ? 0 : GE + 16), !again);
              if (!ODD) mbar_arrive_cl(rempty, GE + 24, !again && j == 0);
#pragma unroll
              for (int k = 4 * VREL + 4; k < 64; k++) asm volatile("" : "+f"(s[k])::"memory");
            }
          }
          a0 += b0; a1 += b1;
          if (redo) break;
          redo = __any_sync(0xffffffffu, !(a0 + a1 < 0x1p70f));
          if (first) {
            uint32_t m0 = __ballot_sync(0xffffffffu, a0 > 0x1p-50f), m1 = __ballot_sync(0xffffffffu, a1 > 0x1p-50f);
            m0 |= m0 >> 1; m1 |= m1 >> 1; m0 |= m0 >> 2; m1 |= m1 >> 2;
            redo = redo || (m0 & m1 & 0x11111111u) != 0x11111111u;
          }
          if (!redo) break;
          again = true;
        }
        l0 += a0; l1 += a1;
        keep(pw);
        keep(o);
        const uint32_t qo = qt >> (j ? 0 : 8);
        if (first) store_chunk<0>(o, i0, i1, qw + unit_of(qo, 0) + frag_offset(warp));
        keep(o);
        bar_sync(2 + wg, 256);
        if (!last) {
          const uint32_t qn = qt >> (j >= 3 ? 8 : 0);
          wg_fence();
          issue_qk(s, qw + unit_of(qn, 0), qw + unit_of(qn, 1), base + unit_of(at, ODD ? 3 : 1));
          wg_commit();
          mbar_wait(bfull + (ODD ? 0 : 16), ODD ? ph ^ 1 : ph);
        }
        if (first) { store_chunk<1>(o, i0, i1, qw + unit_of(qo, 1) + frag_offset(warp)); keep(o); }
        wg_fence();
        issue_pv(o, pw, base + unit_of(at, ODD ? (last ? 3 : 0) : 2), !first);
        wg_commit();
        bar_arrive(3 - wg, 256);
        if (first) { fence_async_smem(); mbar_arrive_pred(bar_ofull + wg * 8, j); PROF(2, tid == 0 && j, 9 + ps * 8); }
        wg_wait<1>();
        keep(s);
        mbar_arrive_cl(rempty, ODD ? 24 : 8, !last);
        PROF(4, tid == 0 && ps == 1, 51 + j);
      };
      uint32_t pa[32], pb[32];
#pragma unroll 1
      for (int j = 0; j < 8; j += 2) {
        step(std::false_type{}, j, pa, pb);
        step(std::true_type{}, j + 1, pb, pa);
      }
      {
        const float i0 = inv_quad_sum(l0), i1 = inv_quad_sum(l1);
        wg_wait<0>();
        keep(o);
        mbar_arrive_cl(rempty, 24);
        store_chunk<0>(o, i0, i1, qw + unit_of(qt, 2) + frag_offset(warp));
        store_chunk<1>(o, i0, i1, qw + unit_of(qt, 3) + frag_offset(warp));
        fence_async_smem();
        mbar_arrive(bar_ofull + wg * 8);
      }
      PROF(2, tid == 0, 10 + ps * 8);
    }

    const int ln = fresh_lane(), g = ln >> 2, tq = ln & 3, ct = warp * 32 + ln;
    const bool lane0 = ln == 0;
    const int lrow0 = warp * 16 + g;
    const int grow0 = rb * 128 + lrow0;
    const uint32_t res = base + OFF_RES, trow = res + wg * 8192 + frag_offset(warp);
    uint32_t xr[32];
    {
      const uint64_t da = make_desc(base + wg * 8192, 16, 1024), db = make_desc(base, 8192, 1024);
      constexpr int U = UNIT / 16;
      constexpr int XU[3] = {9, 12, 13}, WU[3] = {10, 0, 2};
#define HALF_STAGE(acc, st, hf) _Pragma("unroll") for (int kk = 0; kk < 4; kk++) mma_ss<1>(acc, da + XU[st] * U + kk * 2, db + (WU[st] + hf) * U + kk * 128, 1)
      mbar_arrive_pred(bar_ring, lane0);
      PROF(10, ct == PT, 19);
      mbar_wait(gfull + 8, 1);
      mbar_wait(gfull + 16, 1);
      bar_sync(2 + wg, 256);
      wg_fence();
      HALF_STAGE(o, 0, 1);
      HALF_STAGE(o, 1, 1);
      wg_commit();
      mbar_wait(gfull + 24, 1);
      wg_fence();
      HALF_STAGE(o, 2, 1);
      wg_commit();
      bar_arrive(3 - wg, 256);
      cluster_arrive();
      mbar_wait(bar_par, 0);
      uint32_t* xo = g_xch + ((size_t)b * 8 * 256 + ct) * 4;
      const uint32_t* xi = g_xch + ((size_t)(b ^ 2) * 8 * 256 + ct) * 4;
      const uint32_t par1 = (~lds1(par + PAR_CONST + 48) & 1) << 16;
      wg_wait<0>();
      keep(o);
      mbar_arrive_pred(bar_ring + 8, lane0);
      PROF(8, ct == PT, 20);
      uint32_t w[32];
      pack_p(o, w);
#pragma unroll
      for (int i = 0; i < 8; i++) w[4 * i] = (w[4 * i] & ~0x10000u) | par1;
      keep(w);
#pragma unroll
      for (int i = 0; i < 8; i++) st_b128(xo + i * 1024, w[4 * i], w[4 * i + 1], w[4 * i + 2], w[4 * i + 3]);
      PROF(8, ct == PT, 21);
      bar_sync(2 + wg, 256);
      wg_fence();
      HALF_STAGE(s, 0, 0);
      wg_commit();
      uint4 v[8];
#pragma unroll
      for (int i = 0; i < 8; i++) v[i] = ld_b128(xi + i * 1024);
      mbar_wait(bar_xres, 0);
      wg_fence();
      HALF_STAGE(s, 1, 0);
      HALF_STAGE(s, 2, 0);
      wg_commit();
      bar_arrive(3 - wg, 256);
#pragma unroll
      for (int i = 0; i < 16; i += 2) ldmatrix4((trow ^ ((i & 7) << 4)) + (i >> 3) * 16384, xr[2 * i], xr[2 * i + 1], xr[2 * i + 2], xr[2 * i + 3]);
      uint32_t n = 0;
      bool ok;
      do {
        ok = true;
#pragma unroll
        for (int i = 0; i < 8; i++)
          if ((v[i].x & 0x10000u) != par1) { v[i] = ld_b128(xi + i * 1024); ok = false; }
        watchdog(n);
      } while (!ok);
      PROF(8, ct == PT, 22);
      wg_wait<0>();
      keep(s);
      mbar_arrive_pred(bar_ring + 16, lane0);
      PROF(10, ct == PT, 23);
#pragma unroll
      for (int i = 0; i < 8; i++) {
        s[8 * i] += bf_lo(v[i].x); s[8 * i + 1] += __uint_as_float(v[i].x & 0xfffe0000u); s[8 * i + 2] += bf_lo(v[i].y); s[8 * i + 3] += bf_hi(v[i].y);
        s[8 * i + 4] += bf_lo(v[i].z); s[8 * i + 5] += bf_hi(v[i].z); s[8 * i + 6] += bf_lo(v[i].w); s[8 * i + 7] += bf_hi(v[i].w);
      }
    }
    float su0 = 0.f, su1 = 0.f, sq0 = 0.f, sq1 = 0.f, dt0 = 0.f, dt1 = 0.f;
#pragma unroll
    for (int i = 0; i < 16; i++) {
      const uint4 pv = lds4(par + PAR_T1 + i * 64 + tq * 16);
      const uint32_t u0 = hadd2(xr[2 * i], hmul2(pv.x, pack_bf(s[4 * i], s[4 * i + 1])));
      const uint32_t u1 = hadd2(xr[2 * i + 1], hmul2(pv.x, pack_bf(s[4 * i + 2], s[4 * i + 3])));
      xr[2 * i] = u0; xr[2 * i + 1] = u1;
      const float a = bf_lo(u0), c = bf_hi(u0), d = bf_lo(u1), e = bf_hi(u1);
      su0 += a + c; su1 += d + e;
      sq0 = fmaf(a, a, fmaf(c, c, sq0)); sq1 = fmaf(d, d, fmaf(e, e, sq1));
      dt0 = fmaf(a, __uint_as_float(pv.z), fmaf(c, __uint_as_float(pv.w), dt0));
      dt1 = fmaf(d, __uint_as_float(pv.z), fmaf(e, __uint_as_float(pv.w), dt1));
    }
    {
      const bool odd = tq & 1;
      float su = (odd ? su1 : su0) + __shfl_xor_sync(0xffffffffu, odd ? su0 : su1, 1);
      float sq = (odd ? sq1 : sq0) + __shfl_xor_sync(0xffffffffu, odd ? sq0 : sq1, 1);
      float dt = (odd ? dt1 : dt0) + __shfl_xor_sync(0xffffffffu, odd ? dt0 : dt1, 1);
      su += __shfl_xor_sync(0xffffffffu, su, 2); sq += __shfl_xor_sync(0xffffffffu, sq, 2); dt += __shfl_xor_sync(0xffffffffu, dt, 2);
      if (tq < 2) st_b128(g_stats + ((size_t)cj * SEQ + grow0 + tq * 8) * 4, __float_as_uint(su), __float_as_uint(sq), __float_as_uint(dt), tag);
    }
    PROF(8, ct == PT, 29);
    uint32_t mm, ih, il;
    float rbest;
    {
      const uint32_t* sp = g_stats + ((size_t)(tq >> 1) * 4 * SEQ + grow0 + (tq & 1) * 8) * 4;
      uint4 v0 = ld_b128(sp), v1 = ld_b128(sp + SEQ * 4), v2 = ld_b128(sp + SEQ * 8), v3 = ld_b128(sp + SEQ * 12);
#pragma unroll
      for (int i = 0; i < 16; i += 2) stmatrix4((trow ^ ((i & 7) << 4)) + (i >> 3) * 16384, xr[2 * i], xr[2 * i + 1], xr[2 * i + 2], xr[2 * i + 3]);
      const uint4 cst = lds4(par + PAR_CONST);
      const float A1 = __uint_as_float(cst.x) + __uint_as_float(cst.z), A2 = __uint_as_float(cst.y) + __uint_as_float(cst.w);
      uint32_t n = 0;
      while (v0.w != tag || v1.w != tag || v2.w != tag || v3.w != tag) {
        if (v0.w != tag) v0 = ld_b128(sp);
        if (v1.w != tag) v1 = ld_b128(sp + SEQ * 4);
        if (v2.w != tag) v2 = ld_b128(sp + SEQ * 8);
        if (v3.w != tag) v3 = ld_b128(sp + SEQ * 12);
        watchdog(n);
      }
      __syncwarp();
      PROF(8, ct == PT, 30);
      float su = (__uint_as_float(v0.x) + __uint_as_float(v1.x)) + (__uint_as_float(v2.x) + __uint_as_float(v3.x));
      float sq = (__uint_as_float(v0.y) + __uint_as_float(v1.y)) + (__uint_as_float(v2.y) + __uint_as_float(v3.y));
      float dt = (__uint_as_float(v0.z) + __uint_as_float(v1.z)) + (__uint_as_float(v2.z) + __uint_as_float(v3.z));
      su += __shfl_xor_sync(0xffffffffu, su, 2); sq += __shfl_xor_sync(0xffffffffu, sq, 2); dt += __shfl_xor_sync(0xffffffffu, dt, 2);
      const float m = su * (1.f / DM);
      float mb, sd;
      ln_scalars(m, fmaxf(sq * (1.f / DM) - m * m, 0.f), mb, sd);
      const float inv = 1.f / sd;
      rbest = (dt - mb * A1) * inv + A2;
      mm = pack_bf(mb, mb);
      ih = pack_bf(inv, inv);
      const float lo = inv - bf_lo(ih);
      il = pack_bf(lo, lo);
    }
    int ibest;
    {
      const uint32_t bits = __float_as_uint(rbest) & ~3u, key = (int)bits < 0 ? ~bits : bits | 0x80000000u;
      const uint32_t kmax = __reduce_max_sync(0xffffffffu, key);
      const uint32_t row = __reduce_min_sync(0xffffffffu, key == kmax ? lrow0 + (tq & 1) * 8 : 255);
      if (lane0) sts2(par + PAR_RED + warp * 8, kmax, row);
      PROF(8, ct == PT, 38);
      bar_sync(1, 256);
      const uint2 cv = lds2(par + PAR_RED + (ln & 7) * 8);
      const uint32_t k2 = __reduce_max_sync(0xffffffffu, cv.x);
      ibest = __reduce_min_sync(0xffffffffu, cv.x == k2 ? cv.y : 255);
      if (ct < 16) st_relaxed2(g_cand + (cj * 16 + ct) * 32 + rb * 2, (k2 & ~3u) | tag, ((rb * 128 + ibest) << 2) | tag);
    }
    PROF(8, ct == PT, 39);
    if ((ibest >> 4) == warp) {
      const int src = (ibest & 7) * 4 + ((ibest >> 3) & 1), ch = g * 2;
      const uint32_t cm = __shfl_sync(0xffffffffu, mm, src), ch_ = __shfl_sync(0xffffffffu, ih, src), cl = __shfl_sync(0xffffffffu, il, src);
      const uint32_t xa = res + (ch >> 3) * 16384 + ibest * 128 + (((ch & 7) ^ (ibest & 7)) << 4) + tq * 4;
      const uint32_t x0 = lds1(xa), x1 = lds1(xa ^ 16);
      const uint2 p0 = lds2(par + PAR_T2 + ch * 32 + tq * 8), p1 = lds2(par + PAR_T2 + ch * 32 + 32 + tq * 8);
      uint32_t* dst = g_row + rb * 2 * DM + cj * 128 + ln * 4;
      st_pairs(dst, ln_mod(x0, cm, ch_, cl, p0.x, p0.y), ln_mod(x1, cm, ch_, cl, p1.x, p1.y), tag);
      st_pairs(dst + DM, x0, x1, tag);
      __syncwarp();
    }
    PROF(8, ct == PT, 37);
    const uint32_t* inbox = g_cand + b * 32 + (ln & 15) * 2;
    uint2 cv = ld_relaxed2(inbox);
    uint32_t wf[128];
    const uint32_t frow = (ln & 7) + (ln >> 4) * 8;
    const uint32_t wfo = base + (warp & 1) * 8192 + frow * 64 + ((((ln >> 3) & 1) ^ ((frow >> 1) & 3)) << 4);
    if (b < NFFN) {
#pragma unroll
      for (int m = 0; m < 2; m++) {
        const uint32_t wfa = wfo + unit_of(m ? FT_U : FT_G, warp >> 1);
        mbar_wait(bar_box + (m * 4 + (warp >> 1)) * 8, 0);
#pragma unroll
        for (int f = 0; f < 16; f++) {
          const int r = ((f >> 1) * 4 + m * 2 + (f & 1)) * 4;
          ldmatrix4t((wfa ^ ((f & 1) * 32)) + (f >> 1) * 1024, wf[r], wf[r + 1], wf[r + 2], wf[r + 3]);
        }
      }
    }
    PROF(8, ct == PT, 31);
    uint32_t kwin; int iwin;
    uint4 hv[8];
    uint32_t wd[64];
    const uint32_t wda = base + unit_of(FT_D, warp >> 1) + (warp & 1) * 8192 + frow * 128 + ((((ln >> 3) & 1) ^ (ln & 7)) << 4);
#define LOAD_WD(f) ldmatrix4t((wda ^ ((((f) >> 1) & 3) * 32)) + ((f) >> 3) * 4096 + ((f) & 1) * 2048, wd[4 * (f)], wd[4 * (f) + 1], wd[4 * (f) + 2], wd[4 * (f) + 3])
    {
      uint32_t n = 0;
      int cur = -1;
      while (true) {
        const bool valid = !(((cv.x ^ tag) | (cv.y ^ tag)) & 3u);
        const uint32_t key = valid ? cv.x : 0u;
        kwin = __reduce_max_sync(0xffffffffu, key);
        const int src = (__ffs(__ballot_sync(0xffffffffu, key == kwin)) - 1) & 15;
        if (kwin && src != cur) {
          cur = src;
#pragma unroll
          for (int i = 0; i < 8; i++) hv[i] = ld_pairs(g_row + cur * 2 * DM + warp * 128 + i * 16 + tq * 4);
        }
        if (__all_sync(0xffffffffu, valid)) break;
        cv = ld_relaxed2(inbox);
        watchdog(n);
      }
      iwin = __shfl_sync(0xffffffffu, cv.y, cur) >> 2;
    }
    PROF(8, ct == PT, 32);
    const uint32_t* wrow = g_row + (iwin >> 7) * 2 * DM;
    if (b < NFFN) {
      {
        uint32_t n = 0;
        bool ok;
        do {
          ok = true;
#pragma unroll
          for (int i = 0; i < 8; i++)
            if (hv[i].y != tag || hv[i].w != tag) { hv[i] = ld_pairs(wrow + warp * 128 + i * 16 + tq * 4); ok = false; }
          watchdog(n);
        } while (!ok);
      }
      __syncwarp();
      PROF(8, ct == PT, 33);
      float d[8][4];
#pragma unroll
      for (int i = 0; i < 8; i++) { d[i][0] = 0.f; d[i][1] = 0.f; d[i][2] = 0.f; d[i][3] = 0.f; }
#pragma unroll
      for (int ks = 0; ks < 8; ks++) {
#pragma unroll
        for (int mt = 0; mt < 4; mt++) {
          const int r = ks * 16 + mt * 4;
          mma16816(d[mt + (ks & 1) * 4], wf[r], wf[r + 1], wf[r + 2], wf[r + 3], hv[ks].x, hv[ks].z);
        }
      }
      if (tq == 0) {
        const uint32_t dst = base + unit_of(FT_G, warp >> 1) + (warp & 1) * 8192 + g * 32;
        sts4(dst, make_uint4(__float_as_uint(d[0][0] + d[4][0]), __float_as_uint(d[0][2] + d[4][2]), __float_as_uint(d[1][0] + d[5][0]), __float_as_uint(d[1][2] + d[5][2])));
        sts4(dst + 16, make_uint4(__float_as_uint(d[2][0] + d[6][0]), __float_as_uint(d[2][2] + d[6][2]), __float_as_uint(d[3][0] + d[7][0]), __float_as_uint(d[3][2] + d[7][2])));
      }
      bar_sync(1, 256);
      uint32_t ab[4];
      {
        float G = 0.f, U = 0.f;
        const uint32_t src = base + (ln & 7) * 32 + (ln >> 3) * 4;
#pragma unroll
        for (int w8 = 0; w8 < 8; w8++) {
          const uint32_t a = src + ((FT_G >> (w8 >> 1) * 4) & 15) * UNIT + (w8 & 1) * 8192;
          G += __uint_as_float(lds1(a)); U += __uint_as_float(lds1(a + 16));
        }
        mbar_wait(bar_box + (8 + (warp >> 1)) * 8, 0);
#pragma unroll
        for (int f = 0; f < 16; f++) LOAD_WD(f);
        const float act = rbf(silu_f(rbf(G))) * rbf(U);
        const uint32_t pk = pack_bf(act, __shfl_down_sync(0xffffffffu, act, 1));
#pragma unroll
        for (int i = 0; i < 4; i++) ab[i] = __shfl_sync(0xffffffffu, pk, i * 8 + tq * 2);
      }
      PROF(8, ct == PT, 34);
#pragma unroll
      for (int mt = 0; mt < 8; mt++) {
        d[mt][0] = 0.f; d[mt][1] = 0.f; d[mt][2] = 0.f; d[mt][3] = 0.f;
        mma16816(d[mt], wd[mt * 8], wd[mt * 8 + 1], wd[mt * 8 + 2], wd[mt * 8 + 3], ab[0], ab[1]);
        mma16816(d[mt], wd[mt * 8 + 4], wd[mt * 8 + 5], wd[mt * 8 + 6], wd[mt * 8 + 7], ab[2], ab[3]);
      }
#pragma unroll
      for (int i = 0; i < 4; i++) {
        const int m4 = (i >> 1) * 4, e = (i & 1) * 2;
        const float y = (tq & 2) ? ((tq & 1) ? d[m4 + 3][e] : d[m4 + 2][e]) : ((tq & 1) ? d[m4 + 1][e] : d[m4][e]);
        st_relaxed(g_ypart + ((size_t)(warp * 16 + (m4 + tq) * 2 + (i & 1)) * NFFN + b) * 8 + g, tagf(y, tag));
      }
      PROF(8, ct == PT, 35);
    }
    if (ct == 0) { sts2(par + PAR_CONST + 56, kwin, iwin); mbar_arrive(bar_win); }
    {
      const uint32_t mm0 = __shfl_sync(0xffffffffu, mm, ln & ~1), mm1 = __shfl_sync(0xffffffffu, mm, ln | 1);
      const uint32_t ih0 = __shfl_sync(0xffffffffu, ih, ln & ~1), ih1 = __shfl_sync(0xffffffffu, ih, ln | 1);
      const uint32_t il0 = __shfl_sync(0xffffffffu, il, ln & ~1), il1 = __shfl_sync(0xffffffffu, il, ln | 1);
      const bool mine = (iwin >> 4) == rb * 8 + warp;
#pragma unroll 1
      for (int hf = 0; hf < 2; hf++) {
        uint32_t x[16];
#pragma unroll
        for (int i = 0; i < 8; i += 2) ldmatrix4((trow ^ (i << 4)) + hf * 16384, x[2 * i], x[2 * i + 1], x[2 * i + 2], x[2 * i + 3]);
#pragma unroll
        for (int i = 0; i < 8; i++) {
          const uint2 pv = lds2(par + PAR_T2 + (hf * 8 + i) * 32 + tq * 8);
          const uint32_t gb = lds1(par + PAR_T1 + (hf * 8 + i) * 64 + tq * 16 + 4);
          x[2 * i] = hadd2(x[2 * i], hmul2(gb, ln_mod(x[2 * i], mm0, ih0, il0, pv.x, pv.y)));
          x[2 * i + 1] = hadd2(x[2 * i + 1], hmul2(gb, ln_mod(x[2 * i + 1], mm1, ih1, il1, pv.x, pv.y)));
        }
        if (mine) {
          uint32_t* dst = reinterpret_cast<uint32_t*>(P.out + (size_t)grow0 * DM + cj * 128 + hf * 64) + tq;
#pragma unroll
          for (int i = 0; i < 8; i++) {
            if (grow0 != iwin) dst[i * 4] = x[2 * i];
            if (grow0 + 8 != iwin) dst[i * 4 + 4 * DM] = x[2 * i + 1];
          }
        } else {
#pragma unroll
          for (int i = 0; i < 8; i += 2) stmatrix4((trow ^ (i << 4)) + hf * 16384, x[2 * i], x[2 * i + 1], x[2 * i + 2], x[2 * i + 3]);
          fence_async_smem();
          __syncwarp();
          if (elect_one()) {
            tma2d_store(&maps.out, res + hf * 16384 + warp * 2048, cj * 128 + hf * 64, rb * 128 + warp * 16);
            asm volatile("cp.async.bulk.commit_group;" ::: "memory");
          }
        }
      }
      asm volatile("cp.async.bulk.wait_group.read 0;" ::: "memory");
    }
    PROF(8, ct == PT, 11);
    cluster_wait();
  }
}

typedef CUresult (*EncodeFn)(CUtensorMap*, CUtensorMapDataType, cuuint32_t, void*, const cuuint64_t*, const cuuint64_t*,
                             const cuuint32_t*, const cuuint32_t*, CUtensorMapInterleave, CUtensorMapSwizzle,
                             CUtensorMapL2promotion, CUtensorMapFloatOOBfill);

void map2d(EncodeFn enc, CUtensorMap* m, const void* p, uint64_t rows, uint64_t cols, uint32_t brows) {
  cuuint64_t dims[2] = {cols, rows}, strides[1] = {cols * 2};
  cuuint32_t box[2] = {64, brows}, es[2] = {1, 1};
  enc(m, CU_TENSOR_MAP_DATA_TYPE_BFLOAT16, 2, const_cast<void*>(p), dims, strides, box, es, CU_TENSOR_MAP_INTERLEAVE_NONE,
      CU_TENSOR_MAP_SWIZZLE_128B, CU_TENSOR_MAP_L2_PROMOTION_L2_256B, CU_TENSOR_MAP_FLOAT_OOB_FILL_NONE);
}
void map2d_narrow(EncodeFn enc, CUtensorMap* m, const void* p, uint64_t rows, uint64_t cols) {
  cuuint64_t dims[2] = {cols, rows}, strides[1] = {cols * 2};
  cuuint32_t box[2] = {32, 256}, es[2] = {1, 1};
  enc(m, CU_TENSOR_MAP_DATA_TYPE_BFLOAT16, 2, const_cast<void*>(p), dims, strides, box, es, CU_TENSOR_MAP_INTERLEAVE_NONE,
      CU_TENSOR_MAP_SWIZZLE_64B, CU_TENSOR_MAP_L2_PROMOTION_L2_64B, CU_TENSOR_MAP_FLOAT_OOB_FILL_NONE);
}
void map3d(EncodeFn enc, CUtensorMap* m, const void* p, uint64_t rows, uint64_t cols, uint32_t brows, uint32_t nch) {
  cuuint64_t dims[3] = {64, rows, cols / 64}, strides[2] = {cols * 2, 128};
  cuuint32_t box[3] = {64, brows, nch}, es[3] = {1, 1, 1};
  enc(m, CU_TENSOR_MAP_DATA_TYPE_BFLOAT16, 3, const_cast<void*>(p), dims, strides, box, es, CU_TENSOR_MAP_INTERLEAVE_NONE,
      CU_TENSOR_MAP_SWIZZLE_128B, CU_TENSOR_MAP_L2_PROMOTION_L2_256B, CU_TENSOR_MAP_FLOAT_OOB_FILL_NONE);
}

}

extern "C" void kernel_launch(void* const* d_in, const int* in_sizes, int n_in, void* d_out, int out_size) {
  (void)in_sizes; (void)n_in; (void)out_size;
  static EncodeFn enc = nullptr;
  if (!enc) {
    void* fn = nullptr;
    cudaDriverEntryPointQueryResult st;
    cudaGetDriverEntryPoint("cuTensorMapEncodeTiled", &fn, cudaEnableDefault, &st);
    enc = (EncodeFn)fn;
    cudaFuncSetAttribute(fused_kernel, cudaFuncAttributeMaxDynamicSharedMemorySize, SMEM_BYTES);
  }
  Maps maps;
  map2d(enc, &maps.x, d_in[0], SEQ, DM, 128);
  map2d(enc, &maps.out, d_out, SEQ, DM, 16);
  map3d(enc, &maps.wq, d_in[3], DM, NQ, 64, 2);
  map3d(enc, &maps.k, d_in[1], 4 * SK, 128, 128, 1);
  map3d(enc, &maps.v, d_in[2], 4 * SK, 128, 128, 1);
  map3d(enc, &maps.wo, d_in[4], NQ, DM, 64, 2);
  map2d_narrow(enc, &maps.wg, d_in[7], DM, FF);
  map2d_narrow(enc, &maps.wu, d_in[8], DM, FF);
  map3d(enc, &maps.wd, d_in[9], FF, DM, 32, 4);
  map2d_narrow(enc, &maps.wm, d_in[11], DM, NMOD);
  Ptrs p;
  p.x = (const __nv_bfloat16*)d_in[0];
  p.w_r = (const __nv_bfloat16*)d_in[6];
  p.w_gate = (const __nv_bfloat16*)d_in[7];
  p.w_up = (const __nv_bfloat16*)d_in[8];
  p.w_down = (const __nv_bfloat16*)d_in[9];
  p.c = (const __nv_bfloat16*)d_in[10];
  p.w_mod = (const __nv_bfloat16*)d_in[11];
  p.out = (__nv_bfloat16*)d_out;
  fused_kernel<<<NMAIN + NHELP, 384, SMEM_BYTES>>>(maps, p);
}
```

```cpp
#include <cuda_runtime.h>
#include <cuda_bf16.h>
#include <cuda.h>
#include <stdint.h>
#include <type_traits>

#define HD 1
#define HDX 2
#define XF 4
#define XE 32
#define XR 0
#define PF2 1
#define PF2T 1
#define NRS 6
#define FPACE 2
#define GOST 20
#define WB 2
#define WN 16
#define RES0 17
#define RES1 20
#define HU 32
#define NS1 4
#define VREL 7
#define E0 3

namespace {

constexpr int SEQ = 2048, DM = 1024, NQ = 4096, SK = 2048, WIN = 512, FF = 3584, NMOD = 6144;
constexpr int NMAIN = 128, NHELP = 4, NFFN = 112;
constexpr int NSLOT = 4, SLOT_BYTES = 32768, UNIT = 16384, GST_BYTES = 3 * UNIT;
constexpr uint32_t XT0 = 0x9630, XT1 = 0x54DC, XT2 = 0xDC96;
constexpr uint32_t WT0 = 0xA741, WT1 = 0x720A, WT2 = 0x20A7;
constexpr uint32_t AT0 = 0x7420, AT1 = 0x2C0A;
constexpr uint32_t QT = 0x549696DC;
constexpr int OFF_STAGE = 12 * UNIT;
constexpr uint32_t FT_G = 0x761B, FT_U = 0x0CA9, FT_D = 0x382D;
constexpr int OFF_RES = 4 * UNIT;
constexpr int OFF_PAR = 14 * UNIT;
constexpr int OFF_BAR = OFF_PAR + 2048 + 512;
constexpr int SMEM_BYTES = OFF_BAR + 512;
static_assert(SMEM_BYTES <= 232448, "smem");

constexpr int PAR_T1 = 0;
constexpr int PAR_T2 = 1024;
constexpr int PAR_CONST = 1536;
constexpr int PAR_RED = 1600;
constexpr int PAR_SINK = 2176;

struct Maps {
  CUtensorMap x, wq, k, v, wo, wg, wu, wd, wm, out;
};
struct Ptrs {
  const __nv_bfloat16 *x, *w_r, *c, *w_mod, *w_gate, *w_up, *w_down;
  __nv_bfloat16* out;
};

__device__ __align__(1024) uint8_t g_act[16 * 80 * UNIT];
__device__ __align__(128) uint32_t g_mod[NMOD];
__device__ __align__(128) uint32_t g_modp[2 * 2 * DM];
__device__ __align__(128) uint32_t g_ln1[SEQ * 4];
__device__ __align__(128) uint32_t g_cnt_h[16 * 32];
__device__ __align__(128) uint32_t g_cnt_o[128 * 32];
__device__ __align__(128) uint32_t g_xch[NMAIN * 8 * 256 * 4];
__device__ __align__(128) uint32_t g_stats[8 * SEQ * 4];
__device__ __align__(128) uint32_t g_cand[NMAIN * 32];
__device__ __align__(128) uint32_t g_row[16 * 2 * DM];
__device__ __align__(128) uint32_t g_ypart[NMAIN * NFFN * 8];
__device__ uint32_t g_epoch;

__device__ __forceinline__ uint32_t fresh_lane() { uint32_t l; asm volatile("mov.u32 %0, %%laneid;" : "=r"(l)); return l; }
__device__ __forceinline__ uint32_t frag_offset(int warp) {
  const uint32_t l = fresh_lane();
  return ((warp & 3) * 16 + (l & 15)) * 128 + (((l >> 4) ^ (l & 7)) << 4);
}
__device__ __forceinline__ bool elect_one() {
  uint32_t p;
  asm volatile("{ .reg .pred q; elect.sync _|q, 0xffffffff; selp.u32 %0, 1, 0, q; }" : "=r"(p));
  return p;
}
__device__ __forceinline__ uint32_t smem_u32(const void* p) { return (uint32_t)__cvta_generic_to_shared(p); }
__device__ __forceinline__ void mbar_init(uint32_t bar, uint32_t cnt) {
  asm volatile("mbarrier.init.shared::cta.b64 [%0], %1;" ::"r"(bar), "r"(cnt) : "memory");
}
__device__ __forceinline__ void mbar_expect_tx(uint32_t bar, uint32_t bytes) {
  asm volatile("mbarrier.arrive.expect_tx.shared::cta.b64 _, [%0], %1;" ::"r"(bar), "r"(bytes) : "memory");
}
__device__ __forceinline__ void mbar_arrive(uint32_t bar) {
  asm volatile("mbarrier.arrive.shared::cta.b64 _, [%0];" ::"r"(bar) : "memory");
}
__device__ __forceinline__ void mbar_arrive_pred(uint32_t bar, bool p) {
  asm volatile("{ .reg .pred p; setp.ne.b32 p, %1, 0; @p mbarrier.arrive.shared::cta.b64 _, [%0]; }" ::"r"(bar), "r"((int)p) : "memory");
}
__device__ __forceinline__ void mbar_arrive_cl(uint32_t bar, uint32_t off, bool p = true) {
  asm volatile("{ .reg .pred p, q; .reg .b32 a; setp.ne.b32 q, %2, 0; setp.ne.and.b32 p, %0, 0, q; add.u32 a, %0, %1; @p mbarrier.arrive.shared::cluster.b64 _, [a]; }"
               ::"r"(bar), "r"(off), "r"((int)p) : "memory");
}
__device__ __forceinline__ uint32_t mapa(uint32_t addr, uint32_t cta) {
  uint32_t r; asm("mapa.shared::cluster.u32 %0, %1, %2;" : "=r"(r) : "r"(addr), "r"(cta)); return r;
}
__device__ __forceinline__ void cluster_arrive() { asm volatile("barrier.cluster.arrive.relaxed.aligned;" ::: "memory"); }
__device__ __forceinline__ void cluster_wait() { asm volatile("barrier.cluster.wait.aligned;" ::: "memory"); }
__device__ __forceinline__ void watchdog(uint32_t& n) {
}
__device__ __forceinline__ void mbar_wait(uint32_t bar, uint32_t parity) {
  asm volatile("{\n.reg .pred p;\nWAIT_%=:\nmbarrier.try_wait.parity.shared::cta.b64 p, [%0], %1;\n@!p bra WAIT_%=;\n}" ::"r"(bar), "r"(parity) : "memory");
}
__device__ __forceinline__ bool mbar_test(uint32_t bar, uint32_t parity) {
  uint32_t ok;
  asm volatile("{\n.reg .pred p;\nmbarrier.test_wait.parity.shared::cta.b64 p, [%1], %2;\nselp.u32 %0, 1, 0, p;\n}" : "=r"(ok) : "r"(bar), "r"(parity) : "memory");
  return ok;
}
__device__ __forceinline__ uint64_t l2_stream() {
  uint64_t f; asm("createpolicy.fractional.L2::evict_first.b64 %0, 1.0;" : "=l"(f)); return f;
}
__device__ __forceinline__ void tma2d(uint32_t dst, const CUtensorMap* m, int c0, int c1, uint32_t bar) {
  asm volatile("cp.async.bulk.tensor.2d.shared::cluster.global.mbarrier::complete_tx::bytes.L2::cache_hint [%0], [%1, {%3, %4}], [%2], %5;"
               ::"r"(dst), "l"(m), "r"(bar), "r"(c0), "r"(c1), "l"(l2_stream()) : "memory");
}
__device__ __forceinline__ void tma3d_prefetch(const CUtensorMap* m, int c0, int c1, int c2) {
  asm volatile("cp.async.bulk.prefetch.tensor.3d.L2.global.tile [%0, {%1, %2, %3}];" ::"l"(m), "r"(c0), "r"(c1), "r"(c2) : "memory");
}
__device__ __forceinline__ void bulk_load(uint32_t dst, const void* src, uint32_t bytes, uint32_t bar) {
  asm volatile("cp.async.bulk.shared::cluster.global.mbarrier::complete_tx::bytes [%0], [%1], %2, [%3];" ::"r"(dst), "l"(src), "r"(bytes), "r"(bar) : "memory");
}
__device__ __forceinline__ void bulk_load_stream(uint32_t dst, const void* src, uint32_t bytes, uint32_t bar) {
  asm volatile("cp.async.bulk.shared::cluster.global.mbarrier::complete_tx::bytes.L2::cache_hint [%0], [%1], %2, [%3], %4;"
               ::"r"(dst), "l"(src), "r"(bytes), "r"(bar), "l"(l2_stream()) : "memory");
}
__device__ __forceinline__ void tma2d_store(const CUtensorMap* m, uint32_t src, int c0, int c1) {
  asm volatile("cp.async.bulk.tensor.2d.global.shared::cta.bulk_group [%0, {%2, %3}], [%1];" ::"l"(m), "r"(src), "r"(c0), "r"(c1) : "memory");
}
__device__ __forceinline__ void bulk_store(void* dst, uint32_t src, uint32_t bytes) {
  asm volatile("cp.async.bulk.global.shared::cta.bulk_group [%0], [%1], %2;" ::"l"(dst), "r"(src), "r"(bytes) : "memory");
}
__device__ __forceinline__ uint32_t unit_of(uint32_t table, uint32_t i) { return ((table >> (i * 4)) & 15) * UNIT; }
__device__ __forceinline__ void tma3d(uint32_t dst, const CUtensorMap* m, int c0, int c1, int c2, uint32_t bar) {
  asm volatile("cp.async.bulk.tensor.3d.shared::cluster.global.mbarrier::complete_tx::bytes.L2::cache_hint [%0], [%1, {%3, %4, %5}], [%2], %6;"
               ::"r"(dst), "l"(m), "r"(bar), "r"(c0), "r"(c1), "r"(c2), "l"(l2_stream()) : "memory");
}
template <bool STREAM>
__device__ __forceinline__ void tma3d_mc(uint32_t dst, const CUtensorMap* m, int c0, int c1, int c2, uint32_t bar) {
  if (STREAM)
    asm volatile("cp.async.bulk.tensor.3d.shared::cluster.global.mbarrier::complete_tx::bytes.multicast::cluster.L2::cache_hint [%0], [%1, {%3, %4, %5}], [%2], %6, %7;"
                 ::"r"(dst), "l"(m), "r"(bar), "r"(c0), "r"(c1), "r"(c2), "h"((uint16_t)3), "l"(l2_stream()) : "memory");
  else
    asm volatile("cp.async.bulk.tensor.3d.shared::cluster.global.mbarrier::complete_tx::bytes.multicast::cluster [%0], [%1, {%3, %4, %5}], [%2], %6;"
                 ::"r"(dst), "l"(m), "r"(bar), "r"(c0), "r"(c1), "r"(c2), "h"((uint16_t)3) : "memory");
}
__device__ __forceinline__ void prefetch_map(const CUtensorMap* m) {
  asm volatile("prefetch.tensormap [%0];" ::"l"(m) : "memory");
}
__device__ __forceinline__ void fence_async() { asm volatile("fence.proxy.async.global;" ::: "memory"); }
__device__ __forceinline__ void fence_async_smem() { asm volatile("fence.proxy.async.shared::cta;" ::: "memory"); }
__device__ __forceinline__ void bar_sync(int id, int n) { asm volatile("bar.sync %0, %1;" ::"r"(id), "r"(n) : "memory"); }
__device__ __forceinline__ void bar_arrive(int id, int n) { asm volatile("bar.arrive %0, %1;" ::"r"(id), "r"(n) : "memory"); }
__device__ __forceinline__ void wg_fence() { asm volatile("wgmma.fence.sync.aligned;" ::: "memory"); }
__device__ __forceinline__ void wg_commit() { asm volatile("wgmma.commit_group.sync.aligned;" ::: "memory"); }
template <int N> __device__ __forceinline__ void wg_wait() { asm volatile("wgmma.wait_group.sync.aligned %0;" ::"n"(N) : "memory"); }
__device__ __forceinline__ uint64_t make_desc(uint32_t addr, uint32_t lbo, uint32_t sbo) {
  return (uint64_t)((addr & 0x3FFFF) >> 4) | ((uint64_t)(lbo >> 4) << 16) | ((uint64_t)(sbo >> 4) << 32) | (1ull << 62);
}
__device__ __forceinline__ uint32_t ld_relaxed(const uint32_t* p) {
  uint32_t v; asm volatile("ld.relaxed.gpu.global.u32 %0, [%1];" : "=r"(v) : "l"(p) : "memory"); return v;
}
__device__ __forceinline__ uint32_t ld_acquire(const uint32_t* p) {
  uint32_t v; asm volatile("ld.acquire.gpu.global.u32 %0, [%1];" : "=r"(v) : "l"(p) : "memory"); return v;
}
__device__ __forceinline__ uint4 ld_relaxed4(const uint32_t* p) {
  uint4 v; asm volatile("ld.relaxed.gpu.global.v4.u32 {%0,%1,%2,%3}, [%4];" : "=r"(v.x), "=r"(v.y), "=r"(v.z), "=r"(v.w) : "l"(p) : "memory"); return v;
}
__device__ __forceinline__ uint2 ld_relaxed2(const uint32_t* p) {
  uint2 v; asm volatile("ld.relaxed.gpu.global.v2.u32 {%0,%1}, [%2];" : "=r"(v.x), "=r"(v.y) : "l"(p) : "memory"); return v;
}
__device__ __forceinline__ void st_relaxed(uint32_t* p, uint32_t v) {
  asm volatile("st.relaxed.gpu.global.u32 [%0], %1;" ::"l"(p), "r"(v) : "memory");
}
__device__ __forceinline__ void st_relaxed2(uint32_t* p, uint32_t a, uint32_t b) {
  asm volatile("st.relaxed.gpu.global.v2.u32 [%0], {%1,%2};" ::"l"(p), "r"(a), "r"(b) : "memory");
}
__device__ __forceinline__ void st_relaxed4(uint32_t* p, uint32_t a, uint32_t b, uint32_t c, uint32_t d) {
  asm volatile("st.relaxed.gpu.global.v4.u32 [%0], {%1,%2,%3,%4};" ::"l"(p), "r"(a), "r"(b), "r"(c), "r"(d) : "memory");
}
__device__ __forceinline__ void st_b128(uint32_t* p, uint32_t a, uint32_t b, uint32_t c, uint32_t d) {
  asm volatile("{ .reg .b64 u, v; .reg .b128 w; mov.b64 u, {%1, %2}; mov.b64 v, {%3, %4}; mov.b128 w, {u, v}; st.relaxed.gpu.global.b128 [%0], w; }"
               ::"l"(p), "r"(a), "r"(b), "r"(c), "r"(d) : "memory");
}
__device__ __forceinline__ uint4 ld_b128(const uint32_t* p) {
  uint4 r;
  asm volatile("{ .reg .b64 u, v; .reg .b128 w; ld.relaxed.gpu.global.b128 w, [%4]; mov.b128 {u, v}, w; mov.b64 {%0, %1}, u; mov.b64 {%2, %3}, v; }"
               : "=r"(r.x), "=r"(r.y), "=r"(r.z), "=r"(r.w) : "l"(p) : "memory");
  return r;
}
__device__ __forceinline__ void st_pairs(uint32_t* p, uint32_t a, uint32_t b, uint32_t tag) {
  asm volatile("{ .reg .b64 u, v; mov.b64 u, {%1, %3}; mov.b64 v, {%2, %3}; st.relaxed.gpu.global.v2.b64 [%0], {u, v}; }"
               ::"l"(p), "r"(a), "r"(b), "r"(tag) : "memory");
}
__device__ __forceinline__ uint4 ld_pairs(const uint32_t* p) {
  uint4 v;
  asm volatile("{ .reg .b64 u, v; ld.relaxed.gpu.global.v2.b64 {u, v}, [%4]; mov.b64 {%0, %1}, u; mov.b64 {%2, %3}, v; }"
               : "=r"(v.x), "=r"(v.y), "=r"(v.z), "=r"(v.w) : "l"(p) : "memory");
  return v;
}
__device__ __forceinline__ uint2 ld_pair(const uint32_t* p) {
  uint2 v;
  asm volatile("{ .reg .b64 u; ld.relaxed.gpu.global.b64 u, [%2]; mov.b64 {%0, %1}, u; }" : "=r"(v.x), "=r"(v.y) : "l"(p) : "memory");
  return v;
}
__device__ __forceinline__ void red_release(uint32_t* p, uint32_t v) {
  asm volatile("red.release.gpu.global.add.u32 [%0], %1;" ::"l"(p), "r"(v) : "memory");
}
__device__ __forceinline__ uint32_t ldg_nc1(const void* p) {
  uint32_t v;
  asm volatile("ld.global.nc.u32 %0, [%1];" : "=r"(v) : "l"(p));
  return v;
}
__device__ __forceinline__ uint4 ldg_nc4(const void* p) {
  uint4 v; asm volatile("ld.global.nc.L1::no_allocate.v4.u32 {%0,%1,%2,%3}, [%4];" : "=r"(v.x), "=r"(v.y), "=r"(v.z), "=r"(v.w) : "l"(p)); return v;
}
__device__ __forceinline__ void stg4(void* p, uint4 v) {
  asm volatile("st.global.v4.u32 [%0], {%1,%2,%3,%4};" ::"l"(p), "r"(v.x), "r"(v.y), "r"(v.z), "r"(v.w) : "memory");
}
__device__ __forceinline__ void wait_counter(const uint32_t* p, uint32_t target) {
  uint32_t n = 0;
  while ((int)(ld_acquire(p) - target) < 0) { watchdog(n); }
}
__device__ __forceinline__ uint32_t tagf(float v, uint32_t tag) { return (__float_as_uint(v) & ~3u) | tag; }
__device__ __forceinline__ bool tag_ok(uint4 v, uint32_t tag) { return (((v.x ^ tag) | (v.y ^ tag) | (v.z ^ tag) | (v.w ^ tag)) & 3u) == 0; }
__device__ __forceinline__ float untag_sum(uint32_t a, uint32_t b) { return __uint_as_float(a & ~3u) + __uint_as_float(b & ~3u); }
__device__ __forceinline__ uint4 poll4(const uint32_t* p, uint32_t tag) {
  uint4 v = ld_relaxed4(p);
  uint32_t n = 0;
  while (!tag_ok(v, tag)) { v = ld_relaxed4(p); watchdog(n); }
  return v;
}
__device__ __forceinline__ float bf_lo(uint32_t v) { return __uint_as_float(v << 16); }
__device__ __forceinline__ float bf_hi(uint32_t v) { return __uint_as_float(v & 0xffff0000u); }
__device__ __forceinline__ uint32_t pack_bf(float lo, float hi) {
  uint32_t r; asm("cvt.rn.bf16x2.f32 %0, %1, %2;" : "=r"(r) : "f"(hi), "f"(lo)); return r;
}
__device__ __forceinline__ float rbf(float v) { return __uint_as_float(pack_bf(0.f, v) & 0xffff0000u); }
__device__ __forceinline__ uint32_t hmul2(uint32_t a, uint32_t b) {
  uint32_t r; asm("mul.rn.bf16x2 %0, %1, %2;" : "=r"(r) : "r"(a), "r"(b)); return r;
}
__device__ __forceinline__ uint32_t hadd2(uint32_t a, uint32_t b) {
  uint32_t r; asm("add.rn.bf16x2 %0, %1, %2;" : "=r"(r) : "r"(a), "r"(b)); return r;
}
__device__ __forceinline__ uint32_t hsub2(uint32_t a, uint32_t b) {
  uint32_t r; asm("sub.rn.bf16x2 %0, %1, %2;" : "=r"(r) : "r"(a), "r"(b)); return r;
}
__device__ __forceinline__ uint32_t hmax2(uint32_t a, uint32_t b) {
  uint32_t r; asm("max.bf16x2 %0, %1, %2;" : "=r"(r) : "r"(a), "r"(b)); return r;
}
__device__ __forceinline__ float rcp(float x) { float r; asm("rcp.approx.ftz.f32 %0, %1;" : "=f"(r) : "f"(x)); return r; }
__device__ __forceinline__ float ex2(float x) { float r; asm("ex2.approx.ftz.f32 %0, %1;" : "=f"(r) : "f"(x)); return r; }
__device__ __forceinline__ void stmatrix4(uint32_t addr, uint32_t a, uint32_t b, uint32_t c, uint32_t d) {
  asm volatile("stmatrix.sync.aligned.m8n8.x4.shared.b16 [%0], {%1,%2,%3,%4};" ::"r"(addr), "r"(a), "r"(b), "r"(c), "r"(d) : "memory");
}
__device__ __forceinline__ void ldmatrix4(uint32_t addr, uint32_t& a, uint32_t& b, uint32_t& c, uint32_t& d) {
  asm volatile("ldmatrix.sync.aligned.m8n8.x4.shared.b16 {%0,%1,%2,%3}, [%4];" : "=r"(a), "=r"(b), "=r"(c), "=r"(d) : "r"(addr) : "memory");
}
__device__ __forceinline__ void ldmatrix4t(uint32_t addr, uint32_t& a, uint32_t& b, uint32_t& c, uint32_t& d) {
  asm volatile("ldmatrix.sync.aligned.m8n8.x4.trans.shared.b16 {%0,%1,%2,%3}, [%4];" : "=r"(a), "=r"(b), "=r"(c), "=r"(d) : "r"(addr) : "memory");
}
__device__ __forceinline__ void mma16816(float (&d)[4], uint32_t a0, uint32_t a1, uint32_t a2, uint32_t a3, uint32_t b0, uint32_t b1) {
  asm volatile("mma.sync.aligned.m16n8k16.row.col.f32.bf16.bf16.f32 {%0,%1,%2,%3}, {%4,%5,%6,%7}, {%8,%9}, {%0,%1,%2,%3};"
               : "+f"(d[0]), "+f"(d[1]), "+f"(d[2]), "+f"(d[3]) : "r"(a0), "r"(a1), "r"(a2), "r"(a3), "r"(b0), "r"(b1));
}
__device__ __forceinline__ void sts1(uint32_t a, uint32_t v) { asm volatile("st.shared.u32 [%0], %1;" ::"r"(a), "r"(v) : "memory"); }
__device__ __forceinline__ uint4 lds4(uint32_t a) {
  uint4 v; asm volatile("ld.shared.v4.u32 {%0,%1,%2,%3}, [%4];" : "=r"(v.x), "=r"(v.y), "=r"(v.z), "=r"(v.w) : "r"(a) : "memory"); return v;
}
__device__ __forceinline__ uint2 lds2(uint32_t a) {
  uint2 v; asm volatile("ld.shared.v2.u32 {%0,%1}, [%2];" : "=r"(v.x), "=r"(v.y) : "r"(a) : "memory"); return v;
}
__device__ __forceinline__ uint32_t lds1(uint32_t a) {
  uint32_t v; asm volatile("ld.shared.u32 %0, [%1];" : "=r"(v) : "r"(a) : "memory"); return v;
}
__device__ __forceinline__ void sts2(uint32_t a, uint32_t x, uint32_t y) { asm volatile("st.shared.v2.u32 [%0], {%1,%2};" ::"r"(a), "r"(x), "r"(y) : "memory"); }
__device__ __forceinline__ void sts4(uint32_t a, uint4 v) {
  asm volatile("st.shared.v4.u32 [%0], {%1,%2,%3,%4};" ::"r"(a), "r"(v.x), "r"(v.y), "r"(v.z), "r"(v.w) : "memory");
}
__device__ __forceinline__ float silu_f(float v) { return __fdividef(v, 1.f + __expf(-v)); }
__device__ __forceinline__ uint32_t hfma2(uint32_t a, uint32_t b, uint32_t c) {
  uint32_t r; asm("fma.rn.bf16x2 %0, %1, %2, %3;" : "=r"(r) : "r"(a), "r"(b), "r"(c)); return r;
}
__device__ __forceinline__ void split_inv(float sd, uint32_t& ih, uint32_t& il) {
  const float inv = rcp(sd);
  ih = pack_bf(inv, inv);
  const float lo = inv - bf_lo(ih);
  il = pack_bf(lo, lo);
}
__device__ __forceinline__ uint32_t ln_mod(uint32_t x, uint32_t mean2, uint32_t ih, uint32_t il, uint32_t c1, uint32_t sh) {
  const uint32_t d = hsub2(x, mean2);
  return hadd2(hmul2(hfma2(d, ih, hmul2(d, il)), c1), sh);
}

#define R8(a, i) "+f"(a[i]), "+f"(a[i + 1]), "+f"(a[i + 2]), "+f"(a[i + 3]), "+f"(a[i + 4]), "+f"(a[i + 5]), "+f"(a[i + 6]), "+f"(a[i + 7])
#define D64 "{%0,%1,%2,%3,%4,%5,%6,%7,%8,%9,%10,%11,%12,%13,%14,%15,%16,%17,%18,%19,%20,%21,%22,%23,%24,%25,%26,%27,%28,%29,%30,%31," \
            "%32,%33,%34,%35,%36,%37,%38,%39,%40,%41,%42,%43,%44,%45,%46,%47,%48,%49,%50,%51,%52,%53,%54,%55,%56,%57,%58,%59,%60,%61,%62,%63}"
template <int TB>
__device__ __forceinline__ void mma_ss(float (&d)[64], uint64_t da, uint64_t db, int sc) {
  asm volatile("{\n.reg .pred p;\nsetp.ne.b32 p, %66, 0;\n"
               "wgmma.mma_async.sync.aligned.m64n128k16.f32.bf16.bf16 " D64 ", %64, %65, p, 1, 1, 0, %67;\n}"
               : R8(d, 0), R8(d, 8), R8(d, 16), R8(d, 24), R8(d, 32), R8(d, 40), R8(d, 48), R8(d, 56)
               : "l"(da), "l"(db), "r"(sc), "n"(TB));
}
template <int TB>
__device__ __forceinline__ void mma_rs(float (&d)[64], uint32_t a0, uint32_t a1, uint32_t a2, uint32_t a3, uint64_t db, int sc) {
  asm volatile("{\n.reg .pred p;\nsetp.ne.b32 p, %69, 0;\n"
               "wgmma.mma_async.sync.aligned.m64n128k16.f32.bf16.bf16 " D64 ", {%64,%65,%66,%67}, %68, p, 1, 1, %70;\n}"
               : R8(d, 0), R8(d, 8), R8(d, 16), R8(d, 24), R8(d, 32), R8(d, 40), R8(d, 48), R8(d, 56)
               : "r"(a0), "r"(a1), "r"(a2), "r"(a3), "l"(db), "r"(sc), "n"(TB));
}
#define D128 "{%0,%1,%2,%3,%4,%5,%6,%7,%8,%9,%10,%11,%12,%13,%14,%15,%16,%17,%18,%19,%20,%21,%22,%23,%24,%25,%26,%27,%28,%29,%30,%31," \
             "%32,%33,%34,%35,%36,%37,%38,%39,%40,%41,%42,%43,%44,%45,%46,%47,%48,%49,%50,%51,%52,%53,%54,%55,%56,%57,%58,%59,%60,%61,%62,%63," \
             "%64,%65,%66,%67,%68,%69,%70,%71,%72,%73,%74,%75,%76,%77,%78,%79,%80,%81,%82,%83,%84,%85,%86,%87,%88,%89,%90,%91,%92,%93,%94,%95," \
             "%96,%97,%98,%99,%100,%101,%102,%103,%104,%105,%106,%107,%108,%109,%110,%111,%112,%113,%114,%115,%116,%117,%118,%119,%120,%121,%122,%123,%124,%125,%126,%127}"
#define R128(d, e) R8(d, 0), R8(d, 8), R8(d, 16), R8(d, 24), R8(d, 32), R8(d, 40), R8(d, 48), R8(d, 56), \
                   R8(e, 0), R8(e, 8), R8(e, 16), R8(e, 24), R8(e, 32), R8(e, 40), R8(e, 48), R8(e, 56)
__device__ __forceinline__ void mma256_ss(float (&d)[64], float (&e)[64], uint64_t da, uint64_t db, int sc) {
  asm volatile("{\n.reg .pred p;\nsetp.ne.b32 p, %130, 0;\n"
               "wgmma.mma_async.sync.aligned.m64n256k16.f32.bf16.bf16 " D128 ", %128, %129, p, 1, 1, 0, 1;\n}"
               : R128(d, e) : "l"(da), "l"(db), "r"(sc));
}
__device__ __forceinline__ void mma256_rs(float (&d)[64], float (&e)[64], uint32_t a0, uint32_t a1, uint32_t a2, uint32_t a3, uint64_t db) {
  asm volatile("{\n.reg .pred p;\nsetp.ne.b32 p, 1, 0;\n"
               "wgmma.mma_async.sync.aligned.m64n256k16.f32.bf16.bf16 " D128 ", {%128,%129,%130,%131}, %132, p, 1, 1, 1;\n}"
               : R128(d, e) : "r"(a0), "r"(a1), "r"(a2), "r"(a3), "l"(db));
}
template <int N> __device__ __forceinline__ void keep(float (&a)[N]) {
#pragma unroll
  for (int i = 0; i < N; i++) asm volatile("" : "+f"(a[i])::"memory");
}
template <int N> __device__ __forceinline__ void keep(uint32_t (&a)[N]) {
#pragma unroll
  for (int i = 0; i < N; i++) asm volatile("" : "+r"(a[i])::"memory");
}

#define STAMP(idx) do {} while (0)
#define PROF(grp, cond, idx) do {} while (0)

constexpr float SCL2 = 1.4426950408889634f * 0.08838834764831845f;

__device__ __forceinline__ void pack_p(const float (&s)[64], uint32_t (&p)[32]) {
#pragma unroll
  for (int i = 0; i < 32; i++) p[i] = pack_bf(s[2 * i], s[2 * i + 1]);
}

__device__ __forceinline__ void issue_qk(float (&s)[64], uint32_t q0, uint32_t q1, uint32_t kslot) {
  const uint64_t db = make_desc(kslot, 16, 1024), da0 = make_desc(q0, 16, 1024), da1 = make_desc(q1, 16, 1024);
#pragma unroll
  for (int kk = 0; kk < 8; kk++) mma_ss<0>(s, (kk < 4 ? da0 : da1) + (kk & 3) * 2, db + (kk >> 2) * 1024 + (kk & 3) * 2, kk != 0);
}
__device__ __forceinline__ void issue_pv(float (&o)[64], uint32_t (&p)[32], uint32_t vslot, int acc) {
  uint64_t db = make_desc(vslot, 16384, 1024);
#pragma unroll
  for (int kk = 0; kk < 8; kk++)
    mma_rs<1>(o, p[4 * kk], p[4 * kk + 1], p[4 * kk + 2], p[4 * kk + 3], db + kk * 128, kk == 0 ? acc : 1);
}

template <int H>
__device__ __forceinline__ void store_chunk(const float (&a)[64], uint32_t addr) {
#pragma unroll
  for (int i = 8 * H; i < 8 * H + 8; i += 2)
    stmatrix4(addr ^ ((i & 7) << 4), pack_bf(a[4 * i], a[4 * i + 1]), pack_bf(a[4 * i + 2], a[4 * i + 3]),
              pack_bf(a[4 * i + 4], a[4 * i + 5]), pack_bf(a[4 * i + 6], a[4 * i + 7]));
}
template <int H>
__device__ __forceinline__ void store_chunk(const float (&a)[64], float i0, float i1, uint32_t addr) {
#pragma unroll
  for (int i = 8 * H; i < 8 * H + 8; i += 2)
    stmatrix4(addr ^ ((i & 7) << 4), pack_bf(a[4 * i] * i0, a[4 * i + 1] * i0), pack_bf(a[4 * i + 2] * i1, a[4 * i + 3] * i1),
              pack_bf(a[4 * i + 4] * i0, a[4 * i + 5] * i0), pack_bf(a[4 * i + 6] * i1, a[4 * i + 7] * i1));
}
__device__ __forceinline__ float inv_quad_sum(float l) {
  l += __shfl_xor_sync(0xffffffffu, l, 1);
  l += __shfl_xor_sync(0xffffffffu, l, 2);
  return rcp(l);
}

__device__ __forceinline__ void ln_scalars(float mean, float var, float& mb, float& sd) {
  mb = rbf(mean);
  float r; asm("sqrt.approx.ftz.f32 %0, %1;" : "=f"(r) : "f"(rbf(rbf(var) + 1e-5f)));
  sd = rbf(r);
}

__global__ void __cluster_dims__(2, 1, 1) __launch_bounds__(384, 1) fused_kernel(const __grid_constant__ Maps maps, const Ptrs P) {
  extern __shared__ __align__(1024) uint8_t smem_raw[];
  const uint32_t base = smem_u32(smem_raw);
  const int tid = threadIdx.x, lane = tid & 31;
  const int warp = __shfl_sync(0xffffffffu, tid >> 5, 0);
  const int b = blockIdx.x;
  PROF(31, tid == 0, 0);

  if (b >= NMAIN) {
    float* sc = reinterpret_cast<float*>(smem_raw);
    float* red = sc + DM;
    for (int k = tid; k < DM; k += 384) sc[k] = rbf(silu_f(__bfloat162float(P.c[k])));
    __syncthreads();
    if (tid < 256) {
      const int col = 2048 + (b - NMAIN) * 1024 + (tid & 127) * 8, r0 = (tid >> 7) * 512;
      float acc[8];
#pragma unroll
      for (int e = 0; e < 8; e++) acc[e] = 0.f;
#pragma unroll 1
      for (int r = r0; r < r0 + 512; r += HU) {
        uint4 w[HU];
#pragma unroll
        for (int u = 0; u < HU; u++) w[u] = ldg_nc4(P.w_mod + (size_t)(r + u) * NMOD + col);
#pragma unroll
        for (int u = 0; u < HU; u++) {
          float s = sc[r + u];
          acc[0] += s * bf_lo(w[u].x); acc[1] += s * bf_hi(w[u].x); acc[2] += s * bf_lo(w[u].y); acc[3] += s * bf_hi(w[u].y);
          acc[4] += s * bf_lo(w[u].z); acc[5] += s * bf_hi(w[u].z); acc[6] += s * bf_lo(w[u].w); acc[7] += s * bf_hi(w[u].w);
        }
      }
      if (tid >= 128) {
#pragma unroll
        for (int e = 0; e < 8; e++) red[(tid & 127) * 8 + e] = acc[e];
      }
      const uint32_t tag = ld_relaxed(&g_epoch) % 3 + 1;
      bar_sync(1, 256);
      if (tid < 128) {
        uint32_t o[8];
#pragma unroll
        for (int e = 0; e < 8; e++) o[e] = __float_as_uint(rbf(acc[e] + red[tid * 8 + e])) | tag;
        st_relaxed4(g_mod + col, o[0], o[1], o[2], o[3]);
        st_relaxed4(g_mod + col + 4, o[4], o[5], o[6], o[7]);
        const uint4 wr = ldg_nc4(P.w_r + tid * 8);
        const uint32_t wv[4] = {wr.x, wr.y, wr.z, wr.w};
        float dsum = 0.f;
#pragma unroll
        for (int e = 0; e < 8; e++) {
          const float m = bf_hi(o[e]);
          dsum += (b == NMAIN + 2 ? rbf(1.f + m) : m) * ((e & 1) ? bf_hi(wv[e >> 1]) : bf_lo(wv[e >> 1]));
        }
#pragma unroll
        for (int k = 16; k > 0; k >>= 1) dsum += __shfl_xor_sync(0xffffffffu, dsum, k);
        if (lane == 0) st_relaxed(g_mod + (b - NMAIN) * 4 + warp, tagf(dsum, tag));
      }
    }
    PROF(2, tid == 0, 1);
    return;
  }

  const int rank = b & 1;
  const int rb = ((b >> 4) << 1) | rank, cj = (b >> 1) & 7;
  const uint32_t bfull = base + OFF_BAR, bempty = bfull + NSLOT * 8;
  const uint32_t gfull = bempty + NSLOT * 8, gempty = gfull + 32;
  const uint32_t bar_ofull = gempty + 32;
  const uint32_t bar_ofree = bar_ofull + 16;
  const uint32_t bar_par = bar_ofree + 32;
  const uint32_t bar_mod = bar_par + 8;
  const uint32_t bar_pread = bar_mod + 8;
  const uint32_t bar_xres = bar_pread + 8;
  const uint32_t bar_ring = bar_xres + 8;
  const uint32_t bar_box = bar_ring + 24;
  const uint32_t bar_go = bar_box + 96;
  const uint32_t bar_go2 = bar_go + 16;
  const uint32_t bar_cnt = bar_go + 24;
  const uint32_t xfull = bar_go + 32, xempty = xfull + 32;
  const uint32_t bar_hw = xempty + 32, bar_hx = bar_hw + 8;
  const uint32_t bar_hpub = bar_hx + 16;
  const uint32_t bar_win = bar_hpub + 8;
  const uint32_t bar_rx = bar_win + 8;
  const uint32_t bar_res = bar_go + 8;
  const uint32_t stage = base + OFF_STAGE, par = base + OFF_PAR;

  if (warp == 8 && elect_one()) {
    for (int s = 0; s < NSLOT; s++) { mbar_init(bfull + s * 8, 1); mbar_init(bempty + s * 8, 16); }
    for (int s = 0; s < 4; s++) { mbar_init(gfull + s * 8, 1); mbar_init(gempty + s * 8, 16); mbar_init(xfull + s * 8, 1); mbar_init(xempty + s * 8, 8); mbar_init(bar_ofree + s * 8, 1); }
    mbar_init(bar_ofull, 128); mbar_init(bar_ofull + 8, 128);
    mbar_init(bar_par, 64); mbar_init(bar_mod, 256); mbar_init(bar_pread, 8); mbar_init(bar_xres, 1);
    mbar_init(bar_ring, 8); mbar_init(bar_ring + 8, 8); mbar_init(bar_ring + 16, 8);
    mbar_init(bar_go, 1); mbar_init(bar_go2, 1); mbar_init(bar_cnt, 1); mbar_init(bar_hpub, 8); mbar_init(bar_res, 1); mbar_init(bar_win, 1); mbar_init(bar_rx, 1);
    for (int s = 0; s < 12; s++) mbar_init(bar_box + s * 8, 1);
    asm volatile("fence.mbarrier_init.release.cluster;" ::: "memory");
    prefetch_map(&maps.x); prefetch_map(&maps.wq); prefetch_map(&maps.k); prefetch_map(&maps.v);
  }
  if (warp == 9 && elect_one()) {
    mbar_init(bar_hw, 1); mbar_init(bar_hx, 1); mbar_init(bar_hx + 8, 1);
    asm volatile("fence.mbarrier_init.release.cluster;" ::: "memory");
    mbar_expect_tx(bar_hw, 32768);
    mbar_expect_tx(bar_hx, 16384);
    mbar_expect_tx(bar_hx + 8, 16384);
    const __nv_bfloat16* xs = P.x + (size_t)(rb * 128 + cj * 16) * DM;
    bulk_load(base + 2 * GST_BYTES, xs, 16384, bar_hx);
    tma2d(stage, &maps.wm, (b >> 1) * 32, rank * 512, bar_hw);
    tma2d(stage + 16384, &maps.wm, (b >> 1) * 32, rank * 512 + 256, bar_hw);
    bulk_load(base + 3 * GST_BYTES, xs + 8 * DM, 16384, bar_hx + 8);
  }
  cluster_arrive();

  if (warp >= 8) {
    asm volatile("setmaxnreg.dec.sync.aligned.u32 40;");
    if (warp < 10) bar_arrive(1, 320);
    const uint32_t epoch = ld_relaxed(&g_epoch);
    cluster_wait();
    if (warp == 8) {
      const int kvrow = (cj >> 1) * SK + (SK - WIN);
      int wch = cj * 8 + rank * 2;
#pragma unroll 1
      for (int ps = 0; ps < 3; ps++) {
        const CUtensorMap* mw = ps == 2 ? &maps.wo : &maps.wq;
        const uint32_t xt = ps == 1 ? XT1 : XT2, wt = ps == 0 ? WT0 : (ps == 1 ? WT1 : WT2);
        const int nst = ps == 2 ? 32 : 16;
        if (ps) {
          mbar_wait(bar_ofree + (ps - 1) * 16, 0);
          fence_async();
        }
#pragma unroll 1
        for (int i = 0; i < nst; i++) {
          const uint32_t bf = gfull + (i & 3) * 8;
          const int kt = ps == 2 ? (((cj & 1) * 4 + ((i >> 1) & 3)) * 4 + (i >> 3)) * 2 + (i & 1) : (i + (ps ? 0 : b & 14)) & 15;
          const uint32_t wd = base + unit_of(wt, i & 3) + rank * UNIT, xd = base + unit_of(xt, i & 3);
          const uint8_t* xs = g_act + (uint32_t)(rb * 80 + (ps - 1) * 16 + kt) * UNIT;
          if (ps == 0 && i == HD) mbar_wait(bar_mod, 0);
          if (ps && i && i < 4) mbar_wait(bempty + (i == 3 ? 3 : i - 1) * 8, 1);
          mbar_wait(gempty + (i & 3) * 8, ((i >> 2) & 1) ^ 1);
          if (elect_one()) {
            mbar_expect_tx(bf, ps ? GST_BYTES : 2 * UNIT);
            tma3d_mc<true>(wd, mw, 0, (i == 31 ? kt ^ (rank * 32) : kt) * 64, i == 31 ? cj * 2 : wch, bf);
          }
          if (ps) {
            if (i == 16) mbar_wait(bar_cnt, 0);
            if (i == 2) mbar_wait(bempty + 16, 1);
            if (elect_one()) {
              bulk_load_stream(xd, xs, UNIT, bf);
              mbar_arrive_pred(ps == 1 ? bar_go2 : bar_go, i == (ps == 1 ? 15 : GOST - 1));
              mbar_arrive_pred(bar_res, ((1u << RES0 | 1u << RES1) >> i) & 1);
            }
          }
        }
        if (ps == 2) break;
        wch = ps ? ((wch >> 3) ^ rank) * 2 : wch + 4;
#pragma unroll 1
        for (int u = 0; u < 16; u++) {
          const bool isk = (u == 0) || ((u & 1) && u < 15);
          const int blk = (isk ? (u + 1) >> 1 : (u == 15 ? 7 : (u >> 1) - 1)) & 3;
          const uint32_t sl = base + unit_of(ps ? AT1 : AT0, u & 3) + rank * UNIT, bf = bfull + (u & 3) * 8;
          if (u < 4) mbar_wait(gempty + ((u + 1) >> 1) * 8, 1);
          mbar_wait(bempty + (u & 3) * 8, ((u >> 2) & 1) ^ 1);
          if (elect_one()) {
            mbar_expect_tx(bf, SLOT_BYTES);
            tma3d_mc<false>(sl, isk ? &maps.k : &maps.v, 0, kvrow + blk * 128, rank, bf);
          }
        }
      }
      mbar_wait(bar_ring, 0);
      if (elect_one()) {
        mbar_expect_tx(bar_rx, UNIT);
        bulk_load_stream(base + 8 * UNIT, g_act + (uint32_t)(rb * 80 + 16 + 63 - (cj & 1) * 32) * UNIT, UNIT, bar_rx);
      }
      if (b < NFFN) {
#pragma unroll 1
        for (int u = 0; u < 12; u++) {
          if (u == 2 || u == 8) mbar_wait(bar_ring + 8 + (u & 8), 0);
          if (u >= FPACE) mbar_wait(bar_box + (u - FPACE) * 8, 0);
          const uint32_t dst = base + unit_of(u < 4 ? FT_G : (u < 8 ? FT_U : FT_D), u & 3);
          if (elect_one()) {
            mbar_expect_tx(bar_box + u * 8, UNIT);
            if (u < 8) tma2d(dst, u < 4 ? &maps.wg : &maps.wu, b * 32, (u & 3) * 256, bar_box + u * 8);
            else tma3d(dst, &maps.wd, 0, b * 32, (u - 8) * 4, bar_box + u * 8);
          }
        }
      }
    } else if (warp == 9) {
      const uint32_t target = 8 * (epoch + 1);
#pragma unroll 1
      for (int i = 0; i < 16; i++) {
        if (i == HDX) mbar_wait(bar_mod, 0);
        if (i == NRS) {
          wait_counter(&g_cnt_h[rb * 32], target);
          PROF(1, lane == 0, 26);
          fence_async();
        }
        mbar_wait(xempty + (i & 3) * 8, ((i >> 2) & 1) ^ 1);
        if (elect_one()) {
          mbar_expect_tx(xfull + (i & 3) * 8, UNIT);
          if (i < NRS) tma2d(base + (i & 3) * GST_BYTES, &maps.x, ((2 * cj + i) & 15) * 64, rb * 128, xfull + (i & 3) * 8);
          else bulk_load_stream(base + (i & 3) * GST_BYTES, g_act + (uint32_t)(rb * 80 + ((2 * cj + i) & 15)) * UNIT, UNIT, xfull + (i & 3) * 8);
        }
      }
      prefetch_map(&maps.wo);
#pragma unroll 1
      for (int t = 0; t < 4; t++) {
#pragma unroll 1
        for (int w = 0; w < 2; w++) {
          mbar_wait(bar_ofull + w * 8, t & 1);
          uint8_t* dst = g_act + (uint32_t)(rb * 80 + 16 + (cj * 4 + t) * 2) * UNIT + w * 8192;
          if (elect_one()) {
            bulk_store(dst, base + unit_of(QT, 2 * t) + w * 8192, 8192);
            bulk_store(dst + UNIT, base + unit_of(QT, 2 * t + 1) + w * 8192, 8192);
            asm volatile("cp.async.bulk.commit_group;" ::: "memory");
          }
        }
        if (elect_one()) {
          asm volatile("cp.async.bulk.wait_group.read 0;" ::: "memory");
          mbar_arrive(bar_ofree + t * 8);
          asm volatile("cp.async.bulk.wait_group 0;" ::: "memory");
          fence_async();
          red_release(&g_cnt_o[((rb * 4 + t) * 2 + (cj >> 2)) * 32], 2);
          if (t == PF2T) for (int u = 0; u < PF2; u++)
            tma3d_prefetch(&maps.wo, 0, ((((cj & 1) * 4 + (b >> 5)) * 4 + u) * 2 + ((b >> 4) & 1)) * 64, (cj ^ rank) * 2);
        }
        if (t & 1) {
          wait_counter(&g_cnt_o[(rb * 8 + 2 * t - 2 + (cj & 1)) * 32], target);
          wait_counter(&g_cnt_o[(rb * 8 + 2 * t + (cj & 1)) * 32], target);
        }
      }
      wait_counter(&g_cnt_o[(rb * 8 + 7 - (cj & 1)) * 32], target);
      fence_async();
      if (elect_one()) {
        mbar_arrive(bar_cnt);
        PROF(2, true, 27);
        mbar_expect_tx(bar_xres, 32768);
      }
#pragma unroll 1
      for (int u = 0; u < 2; u++) {
        mbar_wait(bar_res, u);
        if (elect_one()) tma2d(base + OFF_RES + u * UNIT, &maps.x, cj * 128 + u * 64, rb * 128, bar_xres);
      }
    } else {
      const int t2 = tid - 320;
      if (t2 == 0) {
        mbar_wait(bar_hpub, 0);
        PROF(1, true, 24);
        red_release(&g_cnt_h[rb * 32], 1);
        PROF(1, true, 25);
        prefetch_map(&maps.wg); prefetch_map(&maps.wu); prefetch_map(&maps.wd); prefetch_map(&maps.out);
      }
      __syncwarp();
      if (b < NFFN) {
        mbar_wait(bar_go2, 0);
        const __nv_bfloat16* pg = ((b & 1) ? P.w_up : P.w_gate) + (b >> 1) * 64 + (size_t)t2 * FF;
        const __nv_bfloat16* pd = P.w_down + (size_t)b * 32768 + t2 * 64;
        PROF(2, t2 == 0, 13);
#pragma unroll 1
        for (int i = 0; i < WN; i += WB) {
          uint32_t v[WB];
#pragma unroll
          for (int u = 0; u < WB; u++)
            asm volatile("ld.global.cg.L2::128B.u32 %0, [%1];" : "=r"(v[u]) : "l"(i < 16 ? pg + (size_t)(i + u) * 64 * FF : pd + (i + u - 16) * 4096));
#pragma unroll
          for (int u = 1; u < WB; u++) v[0] ^= v[u];
          sts1(par + PAR_SINK + t2 * 4, v[0]);
        }
        PROF(2, t2 == 0, 14);
      }
      const uint32_t tag = epoch % 3 + 1;
      mbar_wait(bar_go, 0);
      if (warp == 10) {
        const uint32_t* src = g_mod + 2 * DM + cj * 128 + lane * 4;
        const uint2 wr = *reinterpret_cast<const uint2*>(P.w_r + cj * 128 + lane * 4);
        uint4 vga, vsb, vcb, vgb;
        uint32_t n = 0;
        do {
          vga = ld_relaxed4(src); vsb = ld_relaxed4(src + DM); vcb = ld_relaxed4(src + 2 * DM); vgb = ld_relaxed4(src + 3 * DM);
          watchdog(n);
        } while (!(tag_ok(vga, tag) && tag_ok(vsb, tag) && tag_ok(vcb, tag) && tag_ok(vgb, tag)));
        const float c0 = rbf(1.f + bf_hi(vcb.x)), c1 = rbf(1.f + bf_hi(vcb.y)), c2 = rbf(1.f + bf_hi(vcb.z)), c3 = rbf(1.f + bf_hi(vcb.w));
        sts4(par + PAR_T1 + lane * 32, make_uint4(__byte_perm(vga.x, vga.y, 0x7632), __byte_perm(vgb.x, vgb.y, 0x7632), __float_as_uint(c0 * bf_lo(wr.x)), __float_as_uint(c1 * bf_hi(wr.x))));
        sts4(par + PAR_T1 + lane * 32 + 16, make_uint4(__byte_perm(vga.z, vga.w, 0x7632), __byte_perm(vgb.z, vgb.w, 0x7632), __float_as_uint(c2 * bf_lo(wr.y)), __float_as_uint(c3 * bf_hi(wr.y))));
        sts4(par + PAR_T2 + lane * 16, make_uint4(pack_bf(c0, c1), __byte_perm(vsb.x, vsb.y, 0x7632), pack_bf(c2, c3), __byte_perm(vsb.z, vsb.w, 0x7632)));
      } else if (lane < 4) {
        const uint4 g = poll4(lane < 2 ? g_mod + 5 * DM + b * 8 + lane * 4 : g_mod + 16 - lane * 4, tag);
        if (lane < 2) sts4(par + PAR_CONST + 16 + lane * 16, g);
        else sts2(par + PAR_CONST + (lane - 2) * 8, __float_as_uint(untag_sum(g.x, g.y) + untag_sum(g.z, g.w)), epoch);
      }
      __syncwarp();
#pragma unroll 4
      for (int q = XR; q < XE; q++) st_b128(g_xch + ((size_t)b * 8 * 256 + q * 64 + t2) * 4, (epoch & 1) << 16, 0, 0, 0);
      for (int q = 0; q < 2; q++) st_relaxed4(g_stats + ((size_t)cj * SEQ + rb * 128 + q * 64 + t2) * 4, 0, 0, 0, 0);
      if (b < NFFN)
        for (int q = 0; q < 4; q++) st_relaxed4(g_ypart + ((size_t)(q * 32 + (t2 >> 1)) * NFFN + b) * 8 + (t2 & 1) * 4, 0, 0, 0, 0);
      st_relaxed4(g_row + rb * 2 * DM + (t2 >> 5) * DM + cj * 128 + (t2 & 31) * 4, 0, 0, 0, 0);
      if (t2 < 16) st_relaxed2(g_cand + (cj * 16 + t2) * 32 + rb * 2, 0, 0);
      __threadfence();
      mbar_arrive(bar_par);
    }
    __syncwarp();
    cluster_arrive();
    {
      const uint32_t tag = epoch % 3 + 1, t3 = tid - 256;
      mbar_wait(bar_win, 0);
      const uint2 win = lds2(par + PAR_CONST + 56);
      const uint32_t* fsrc = g_row + (win.y >> 7) * 2 * DM + (b >> 1) * 16 + (t3 & 3) * 4 + (b & 1) * 2;
      const uint32_t* ysrc = g_ypart + ((size_t)b * NFFN + min(t3, NFFN - 1)) * 8;
      uint2 fh = ld_pair(fsrc), fx = ld_pair(fsrc + DM);
      uint4 ya = ld_relaxed4(ysrc), yb = ld_relaxed4(ysrc + 4);
      const float rwin = __uint_as_float(((int)win.x < 0 ? win.x & 0x7fffffffu : ~win.x) & ~3u);
      const float rs = rbf(rcp(1.f + __expf(-rbf(rwin))));
      uint32_t n = 0;
      while (fh.y != tag || fx.y != tag) { fh = ld_pair(fsrc); fx = ld_pair(fsrc + DM); watchdog(n); }
      while (!(tag_ok(ya, tag) && tag_ok(yb, tag))) { ya = ld_relaxed4(ysrc); yb = ld_relaxed4(ysrc + 4); watchdog(n); }
      __syncwarp();
      PROF(8, t3 == 0, 5);
      const uint32_t msk = t3 < NFFN ? ~3u : 0u;
      float y[8] = {__uint_as_float(ya.x & msk), __uint_as_float(ya.y & msk), __uint_as_float(ya.z & msk), __uint_as_float(ya.w & msk),
                    __uint_as_float(yb.x & msk), __uint_as_float(yb.y & msk), __uint_as_float(yb.z & msk), __uint_as_float(yb.w & msk)};
#pragma unroll
      for (int h = 4; h > 0; h >>= 1) {
        const bool up = lane & (h * 4);
#pragma unroll
        for (int e = 0; e < h; e++) y[e] = (up ? y[e + h] : y[e]) + __shfl_xor_sync(0xffffffffu, up ? y[e] : y[e + h], h * 4);
      }
      y[0] += __shfl_xor_sync(0xffffffffu, y[0], 1);
      y[0] += __shfl_xor_sync(0xffffffffu, y[0], 2);
      if ((lane & 3) == 0) sts1(par + PAR_RED + 64 + t3, __float_as_uint(y[0]));
      bar_sync(4, 128);
      if (t3 < 4) {
        float y0 = 0.f, y1 = 0.f;
#pragma unroll
        for (int w4 = 0; w4 < 4; w4++) {
          const uint2 v = lds2(par + PAR_RED + 64 + w4 * 32 + t3 * 8);
          y0 += __uint_as_float(v.x); y1 += __uint_as_float(v.y);
        }
        const uint2 gv = lds2(par + PAR_CONST + 16 + t3 * 8);
        const uint32_t upd = hmul2(pack_bf(y0, y1), pack_bf(rs, rs));
        *reinterpret_cast<uint32_t*>(P.out + (size_t)win.y * DM + b * 8 + t3 * 2) =
            hadd2(fx.x, hmul2(__byte_perm(gv.x, gv.y, 0x7632), hadd2(fh.x, upd)));
        if (b == 0 && t3 == 0) st_relaxed(&g_epoch, epoch + 1);
      }
      PROF(31, t3 == 0, 36);
    }
    cluster_wait();
  } else {
    const int wg = warp >> 2;

    uint32_t tag;
    {
      uint32_t* const pmod = g_modp + rank * 2 * DM + (b >> 1) * 32 + lane;
      uint32_t* const pln = g_ln1 + (rb * 128 + cj * 16 + warp) * 4;
      const uint32_t cv = ldg_nc1(P.c + rank * 512 + tid * 2);
      const uint32_t epoch = ld_relaxed(&g_epoch);
      if (warp == 0) st_relaxed(pmod, 0);
      if (lane == 0) { st_relaxed2(pln, 0, 0); st_relaxed2(pln + 32, 0, 0); }
      asm volatile("setmaxnreg.inc.sync.aligned.u32 232;");
      sts1(par + tid * 4, pack_bf(silu_f(bf_lo(cv)), silu_f(bf_hi(cv))));
      bar_sync(1, 320);
      tag = epoch % 3 + 1;
#pragma unroll
      for (int part = 0; part < 3; part++) {
        if (part != 1) {
          const uint32_t xa = base + (2 + part / 2) * GST_BYTES + warp * 2048 + lane * 16;
          mbar_wait(bar_hx + part * 4, 0);
          float s0 = 0.f, s1 = 0.f, q0 = 0.f, q1 = 0.f;
#pragma unroll
          for (int q = 0; q < 4; q++) {
            const uint4 xv = lds4(xa + q * 512);
            const uint32_t u[4] = {xv.x, xv.y, xv.z, xv.w};
#pragma unroll
            for (int e = 0; e < 4; e++) { const float lo = bf_lo(u[e]), hi = bf_hi(u[e]); s0 += lo; s1 += hi; q0 += lo * lo; q1 += hi * hi; }
          }
          s0 += s1; q0 += q1;
#pragma unroll
          for (int o = 16; o > 0; o >>= 1) { s0 += __shfl_xor_sync(0xffffffffu, s0, o); q0 += __shfl_xor_sync(0xffffffffu, q0, o); }
          const float mean = s0 * (1.f / DM);
          float mb, sd;
          ln_scalars(mean, fmaxf(q0 * (1.f / DM) - mean * mean, 0.f), mb, sd);
          if (lane == 0) st_relaxed2(pln + part * 16, __float_as_uint(mb) | tag, __float_as_uint(sd) | tag);
          PROF(1, tid == 0 && part == 2, 4);
        } else {
          float acc[8];
#pragma unroll
          for (int e = 0; e < 8; e++) acc[e] = 0.f;
          const uint32_t wa = stage + (tid >> 2) * 64 + (((tid ^ (tid >> 3)) & 3) << 4), sa = par + (tid >> 3) * 4, sh = (tid & 4) ? 0x3244 : 0x1044;
          mbar_wait(bar_hw, 0);
#pragma unroll
          for (int p = 0; p < 8; p++) {
            const uint4 w = lds4(wa + p * 4096);
            const float s = __uint_as_float(__byte_perm(lds1(sa + p * 128), 0, sh));
            acc[0] += s * bf_lo(w.x); acc[1] += s * bf_hi(w.x); acc[2] += s * bf_lo(w.y); acc[3] += s * bf_hi(w.y);
            acc[4] += s * bf_lo(w.z); acc[5] += s * bf_hi(w.z); acc[6] += s * bf_lo(w.w); acc[7] += s * bf_hi(w.w);
          }
#pragma unroll
          for (int e = 0; e < 4; e++) {
            const bool up = lane & 16;
            acc[e] = (up ? acc[e + 4] : acc[e]) + __shfl_xor_sync(0xffffffffu, up ? acc[e] : acc[e + 4], 16);
          }
#pragma unroll
          for (int e = 0; e < 2; e++) {
            const bool up = lane & 8;
            acc[e] = (up ? acc[e + 2] : acc[e]) + __shfl_xor_sync(0xffffffffu, up ? acc[e] : acc[e + 2], 8);
          }
          {
            const bool up = lane & 4;
            acc[0] = (up ? acc[1] : acc[0]) + __shfl_xor_sync(0xffffffffu, up ? acc[0] : acc[1], 4);
          }
          sts1(par + 1024 + warp * 128 + ((lane & 3) * 8 + (lane >> 2)) * 4, __float_as_uint(acc[0]));
          bar_sync(1, 256);
          if (warp == 0) {
            float s = 0.f;
#pragma unroll
            for (int w8 = 0; w8 < 8; w8++) s += __uint_as_float(lds1(par + 1024 + w8 * 128 + lane * 4));
            st_relaxed(pmod, (__float_as_uint(s) & ~3u) | tag);
          }
          PROF(1, tid == 0, 3);
        }
      }
      {
        uint2 s0 = ld_relaxed2(g_ln1 + (rb * 128 + (tid & 127)) * 4);
        uint4 v[4];
#pragma unroll
        for (int q = 0; q < 4; q++) v[q] = ld_relaxed4(g_modp + q * DM + tid * 4);
        {
          uint32_t n = 0;
          while (!(tag_ok(v[0], tag) && tag_ok(v[1], tag) && tag_ok(v[2], tag) && tag_ok(v[3], tag))) {
#pragma unroll
            for (int q = 0; q < 4; q++)
              if (!tag_ok(v[q], tag)) v[q] = ld_relaxed4(g_modp + q * DM + tid * 4);
            if (((s0.x ^ tag) | (s0.y ^ tag)) & 3u) s0 = ld_relaxed2(g_ln1 + (rb * 128 + (tid & 127)) * 4);
            watchdog(n);
          }
        }
        const uint32_t d = stage + (tid >> 2) * 64 + (tid & 1) * 32 + (tid & 2) * 2;
        sts1(d, pack_bf(1.f + rbf(untag_sum(v[1].x, v[3].x)), 1.f + rbf(untag_sum(v[1].y, v[3].y))));
        sts1(d + 16, pack_bf(1.f + rbf(untag_sum(v[1].z, v[3].z)), 1.f + rbf(untag_sum(v[1].w, v[3].w))));
        sts1(d + 8, pack_bf(untag_sum(v[0].x, v[2].x), untag_sum(v[0].y, v[2].y)));
        sts1(d + 24, pack_bf(untag_sum(v[0].z, v[2].z), untag_sum(v[0].w, v[2].w)));
        if (wg == 0) {
          uint32_t n = 0;
          while (((s0.x ^ tag) | (s0.y ^ tag)) & 3u) { s0 = ld_relaxed2(g_ln1 + (rb * 128 + tid) * 4); watchdog(n); }
          uint32_t ih, il;
          split_inv(bf_hi(s0.y), ih, il);
          sts4(stage + 4096 + tid * 16, make_uint4(__byte_perm(s0.x, 0, 0x3232), ih, il, 0));
        }
        mbar_arrive(bar_mod);
      }
      cluster_wait();
      if (wg == 1) bar_arrive(2, 256);
      mbar_wait(bar_mod, 0);
      PROF(1, tid == 0, 2);
    }

    float f0 = 0.f, f1 = 0.f;
    const uint32_t rempty = lane < 2 ? mapa(bempty, lane & 1) : 0;
    constexpr uint32_t GE = NSLOT * 8 + 32;
    float o[64], s[64];
#pragma unroll 1
    for (int ps = 0; ps < 3; ps++) {
      {
        const uint32_t xt = ps == 1 ? XT1 : XT2, wt = ps == 1 ? WT1 : WT2;
        const int nst = ps == 2 ? 28 : 14;
        if (ps == 0) {
          float ga[64], gb[64];
#pragma unroll
          for (int i = 0; i < 64; i++) { ga[i] = 0.f; gb[i] = 0.f; }
          uint32_t a[2][16];
          const uint32_t l = fresh_lane();
          const uint4 r0 = lds4(stage + 4096 + (warp * 16 + (l >> 2)) * 16), r1 = lds4(stage + 4096 + 128 + (warp * 16 + (l >> 2)) * 16);
          auto transform = [&](int i, uint32_t (&f)[16], uint32_t z) {
            const uint32_t ad = base + (i & 3) * GST_BYTES + wg * 8192 + frag_offset(warp) + z;
            mbar_wait(xfull + (i & 3) * 8, i >> 2);
#pragma unroll
            for (int kk = 0; kk < 4; kk++) ldmatrix4(ad ^ (kk * 32), f[4 * kk], f[4 * kk + 1], f[4 * kk + 2], f[4 * kk + 3]);
#pragma unroll
            for (int kk = 0; kk < 4; kk++) {
              const uint4 m = lds4(stage + (l & 3) * 16 + ((2 * cj + i) & 15) * 256 + kk * 64);
              f[4 * kk] = ln_mod(f[4 * kk], r0.x, r0.y, r0.z, m.x, m.z);
              f[4 * kk + 1] = ln_mod(f[4 * kk + 1], r1.x, r1.y, r1.z, m.x, m.z);
              f[4 * kk + 2] = ln_mod(f[4 * kk + 2], r0.x, r0.y, r0.z, m.y, m.w);
              f[4 * kk + 3] = ln_mod(f[4 * kk + 3], r1.x, r1.y, r1.z, m.y, m.w);
            }
            keep(f);
            mbar_arrive_pred(xempty + (i & 3) * 8, l == 0);
          };
          auto publish = [&](int u, uint32_t (&f)[16]) {
            const uint32_t sc = stage + 8192 + wg * 8192;
#pragma unroll
            for (int kk = 0; kk < 4; kk++) stmatrix4((sc + frag_offset(warp)) ^ (kk * 32), f[4 * kk], f[4 * kk + 1], f[4 * kk + 2], f[4 * kk + 3]);
            __syncwarp();
            const uint32_t src = sc + (warp & 3) * 2048 + l * 16;
            uint8_t* dst = g_act + (uint32_t)(rb * 80 + cj * 2 + u) * UNIT + warp * 2048 + l * 16;
#pragma unroll
            for (int p4 = 0; p4 < 4; p4++) stg4(dst + p4 * 512, lds4(src + p4 * 512));
            __syncwarp();
            if (u == 1) mbar_arrive_pred(bar_hpub, l == 0);
          };
          auto multiply = [&](int i, uint32_t (&f)[16]) {
            mbar_wait(gfull + (i & 3) * 8, i >> 2);
            const uint64_t db = make_desc(base + (i & 3) * GST_BYTES + UNIT, 8192, 1024);
            wg_fence();
#pragma unroll
            for (int kk = 0; kk < 4; kk++) mma256_rs(ga, gb, f[4 * kk], f[4 * kk + 1], f[4 * kk + 2], f[4 * kk + 3], db + kk * 128);
            wg_commit();
          };
          transform(0, a[0], 0); publish(0, a[0]); transform(1, a[1], 0); multiply(0, a[0]); publish(1, a[1]);
#pragma unroll
          for (int i = 1; i < NRS; i++) {
            if (i >= 2) {
              uint32_t z = r0.w;
#pragma unroll
              for (int k = 0; k < 16; k += 2) asm volatile("lop3.b32 %0, %1, %2, %0, 0xA8;" : "+r"(z) : "r"(a[i & 1][k]), "r"(a[i & 1][k + 1]));
              transform(i, a[i & 1], z);
            }
            multiply(i, a[i & 1]);
            wg_wait<1>();
            mbar_arrive_cl(rempty, GE + ((i + 3) & 3) * 8);
          }
          mbar_arrive_pred(bar_pread, l == 0);
#pragma unroll 1
          for (int i = NRS; i < 14; i++) {
            mbar_wait(xfull + (i & 3) * 8, (i >> 2) & 1);
            mbar_wait(gfull + (i & 3) * 8, (i >> 2) & 1);
            const uint32_t xa = base + (i & 3) * GST_BYTES;
            const uint64_t da = make_desc(xa + wg * 8192, 16, 1024), db = make_desc(xa + UNIT, 8192, 1024);
            if (i == 13) bar_sync(2 + wg, 256);
            wg_fence();
#pragma unroll
            for (int kk = 0; kk < 4; kk++) mma256_ss(ga, gb, da + kk * 2, db + kk * 128, 1);
            wg_commit();
            if (i == 13) bar_arrive(3 - wg, 256);
            wg_wait<1>();
            uint32_t z = r0.w;
#pragma unroll
            for (int k = 0; k < 16; k += 2) asm volatile("lop3.b32 %0, %1, %2, %0, 0xA8;" : "+r"(z) : "r"(a[1][k]), "r"(a[1][k + 1]));
            mbar_arrive_cl(rempty, GE + ((i + 3) & 3) * 8 + z);
            mbar_arrive_pred(xempty + ((i + 3) & 3) * 8, l == 0 && i != NRS);
          }
          mbar_wait(xfull + 16, 1);
          mbar_wait(xfull + 24, 1);
          wg_wait<0>();
          keep(ga); keep(gb);
#pragma unroll
          for (int i = 0; i < 64; i++) {
            asm volatile("mov.b32 %0, %1;" : "=f"(s[i]) : "f"(ga[i]));
            asm volatile("mov.b32 %0, %1;" : "=f"(o[i]) : "f"(gb[i]));
          }
        } else {
          float ga[64], gb[64];
#pragma unroll
          for (int i = 0; i < 64; i++) {
            asm volatile("mov.b32 %0, %1;" : "=f"(ga[i]) : "f"(s[i]));
            asm volatile("mov.b32 %0, %1;" : "=f"(gb[i]) : "f"(o[i]));
          }
#pragma unroll 1
          for (int i = 0; i < nst; i++) {
            mbar_wait(gfull + (i & 3) * 8, (i >> 2) & 1);
            const uint64_t da = make_desc(base + unit_of(xt, i & 3) + wg * 8192, 16, 1024), db = make_desc(base + unit_of(wt, i & 3), 8192, 1024);
            if (i == nst - 1) bar_sync(2 + wg, 256);
            wg_fence();
#pragma unroll
            for (int kk = 0; kk < 4; kk++) mma256_ss(ga, gb, da + kk * 2, db + kk * 128, kk ? 1 : i);
            wg_commit();
            if (i == nst - 1) bar_arrive(3 - wg, 256);
            wg_wait<1>();
            mbar_arrive_cl(rempty, GE + ((i + 3) & 3) * 8, i != 0);
            PROF(4, tid == 0 && (i & 3) == 0, 40 + (ps - 1) * 4 + i / 4);
          }
          wg_wait<0>();
          keep(ga); keep(gb);
#pragma unroll
          for (int i = 0; i < 64; i++) {
            asm volatile("mov.b32 %0, %1;" : "=f"(s[i]) : "f"(ga[i]));
            asm volatile("mov.b32 %0, %1;" : "=f"(o[i]) : "f"(gb[i]));
          }
        }
        mbar_arrive_cl(rempty, GE + (ps == 2 ? 24 : 8));
        if (ps == 2) break;
      }
      const uint32_t qw = base + wg * 8192, qt = QT >> (16 * ps), at = ps ? AT1 : AT0;
      {
        const uint32_t wt = ps ? WT1 : WT0;
        const uint64_t da0 = make_desc(qw + unit_of(qt, 2), 16, 1024), da1 = make_desc(qw + unit_of(qt, 3), 16, 1024);
        const uint64_t db0 = make_desc(base + unit_of(wt, 2), 8192, 1024), db1 = make_desc(base + unit_of(wt, 3), 8192, 1024);
        mbar_wait(gfull + 16, 1);
        mbar_wait(gfull + 24, 1);
        bar_sync(2 + wg, 256);
        wg_fence();
#pragma unroll
        for (int kk = 0; kk < 8; kk++) mma_ss<1>(s, (kk < 4 ? da0 : da1) + (kk & 3) * 2, (kk < 4 ? db0 : db1) + (kk & 3) * 128, 1);
        wg_commit();
        bar_arrive(3 - wg, 256);
        mbar_wait(ps == 0 ? bar_pread : bar_ofree + 8, 0);
        mbar_wait(bfull, 0);
        wg_wait<0>();
        keep(s);
        PROF(2, tid == 0, 8 + ps * 8);
        store_chunk<0>(s, qw + unit_of(qt, 0) + frag_offset(warp));
        store_chunk<1>(s, qw + unit_of(qt, 1) + frag_offset(warp));
        fence_async_smem();
        bar_sync(2 + wg, 256);
        wg_fence();
        issue_qk(s, qw + unit_of(qt, 0), qw + unit_of(qt, 1), base + unit_of(at, 0));
        wg_commit();
#pragma unroll
        for (int kk = 0; kk < 8; kk++) mma_ss<1>(o, (kk < 4 ? da0 : da1) + (kk & 3) * 2, (kk < 4 ? db0 : db1) + UNIT / 16 + (kk & 3) * 128, 1);
        wg_commit();
        bar_arrive(3 - wg, 256);
        wg_wait<1>();
        keep(s);
        mbar_arrive_cl(rempty, 0);
      }
      PROF(4, tid == 0 && ps == 1, 61);
      float l0 = 0.25f, l1 = 0.25f;
      auto step = [&](auto odd_c, const int j, uint32_t (&pw)[32], uint32_t (&pr)[32]) {
        constexpr bool ODD = decltype(odd_c)::value;
        const bool first = !ODD && (j & 2) == 0, last = ODD && j == 7;
        const uint32_t ph = (j >> 1) & 1;
        float i0, i1, a0, a1;
        if (first) { i0 = inv_quad_sum(l0); i1 = inv_quad_sum(l1); l0 = 0.f; l1 = 0.f; }
        bool redo = !ODD && (j | ps) == 0, again = false;
        while (true) {
          if (redo) {
            float m0 = fmaxf(s[0], s[1]), m1 = fmaxf(s[2], s[3]);
#pragma unroll
            for (int i = 1; i < 16; i++) { m0 = fmaxf(m0, fmaxf(s[4 * i], s[4 * i + 1])); m1 = fmaxf(m1, fmaxf(s[4 * i + 2], s[4 * i + 3])); }
            m0 = fmaxf(m0, __shfl_xor_sync(0xffffffffu, m0, 1)); m1 = fmaxf(m1, __shfl_xor_sync(0xffffffffu, m1, 1));
            m0 = fmaxf(m0, __shfl_xor_sync(0xffffffffu, m0, 2)); m1 = fmaxf(m1, __shfl_xor_sync(0xffffffffu, m1, 2));
            m0 *= SCL2; m1 *= SCL2;
            if (!first) {
              m0 = fmaxf(m0, f0); m1 = fmaxf(m1, f1);
              const float c0 = ex2(f0 - m0), c1 = ex2(f1 - m1);
              l0 *= c0; l1 *= c1;
              wg_wait<0>();
              keep(o);
#pragma unroll
              for (int i = 0; i < 16; i++) { o[4 * i] *= c0; o[4 * i + 1] *= c0; o[4 * i + 2] *= c1; o[4 * i + 3] *= c1; }
            }
            f0 = m0; f1 = m1;
          }
          float b0 = 0.f, b1 = 0.f;
          a0 = 0.f; a1 = 0.f;
#pragma unroll
          for (int i = 0; i < 16; i++) {
            const float e0 = ex2(fmaf(s[4 * i], SCL2, -f0)), e1 = ex2(fmaf(s[4 * i + 1], SCL2, -f0));
            const float e2 = ex2(fmaf(s[4 * i + 2], SCL2, -f1)), e3 = ex2(fmaf(s[4 * i + 3], SCL2, -f1));
            a0 += e0; b0 += e1; a1 += e2; b1 += e3;
            pw[2 * i] = pack_bf(e0, e1); pw[2 * i + 1] = pack_bf(e2, e3);
            if (i == VREL) {
#pragma unroll
              for (int k = 0; k < 2 * VREL + 2; k++) asm volatile("" : "+r"(pw[k])::"memory");
              mbar_wait(bfull + (ODD ? 24 : 8), ph);
              wg_wait<0>();
              mbar_arrive_cl(rempty, ODD ? 16 : (j ? 0 : GE + 16), !again);
              if (!ODD) mbar_arrive_cl(rempty, GE + 24, !again && j == 0);
#pragma unroll
              for (int k = 4 * VREL + 4; k < 64; k++) asm volatile("" : "+f"(s[k])::"memory");
            }
          }
          a0 += b0; a1 += b1;
          if (redo) break;
          redo = __any_sync(0xffffffffu, !(a0 + a1 < 0x1p70f));
          if (first) {
            uint32_t m0 = __ballot_sync(0xffffffffu, a0 > 0x1p-50f), m1 = __ballot_sync(0xffffffffu, a1 > 0x1p-50f);
            m0 |= m0 >> 1; m1 |= m1 >> 1; m0 |= m0 >> 2; m1 |= m1 >> 2;
            redo = redo || (m0 & m1 & 0x11111111u) != 0x11111111u;
          }
          if (!redo) break;
          again = true;
        }
        l0 += a0; l1 += a1;
        keep(pw);
        keep(o);
        const uint32_t qo = qt >> (j ? 0 : 8);
        if (first) store_chunk<0>(o, i0, i1, qw + unit_of(qo, 0) + frag_offset(warp));
        keep(o);
        bar_sync(2 + wg, 256);
        if (!last) {
          const uint32_t qn = qt >> (j >= 3 ? 8 : 0);
          wg_fence();
          issue_qk(s, qw + unit_of(qn, 0), qw + unit_of(qn, 1), base + unit_of(at, ODD ? 3 : 1));
          wg_commit();
          mbar_wait(bfull + (ODD ? 0 : 16), ODD ? ph ^ 1 : ph);
        }
        if (first) { store_chunk<1>(o, i0, i1, qw + unit_of(qo, 1) + frag_offset(warp)); keep(o); }
        wg_fence();
        issue_pv(o, pw, base + unit_of(at, ODD ? (last ? 3 : 0) : 2), !first);
        wg_commit();
        bar_arrive(3 - wg, 256);
        if (first) { fence_async_smem(); mbar_arrive_pred(bar_ofull + wg * 8, j); PROF(2, tid == 0 && j, 9 + ps * 8); }
        wg_wait<1>();
        keep(s);
        mbar_arrive_cl(rempty, ODD ? 24 : 8, !last);
        PROF(4, tid == 0 && ps == 1, 51 + j);
      };
      uint32_t pa[32], pb[32];
#pragma unroll 1
      for (int j = 0; j < 8; j += 2) {
        step(std::false_type{}, j, pa, pb);
        step(std::true_type{}, j + 1, pb, pa);
      }
      {
        const float i0 = inv_quad_sum(l0), i1 = inv_quad_sum(l1);
        wg_wait<0>();
        keep(o);
        mbar_arrive_cl(rempty, 24);
        store_chunk<0>(o, i0, i1, qw + unit_of(qt, 2) + frag_offset(warp));
        store_chunk<1>(o, i0, i1, qw + unit_of(qt, 3) + frag_offset(warp));
        fence_async_smem();
        mbar_arrive(bar_ofull + wg * 8);
      }
      PROF(2, tid == 0, 10 + ps * 8);
    }

    const int ln = fresh_lane(), g = ln >> 2, tq = ln & 3, ct = warp * 32 + ln;
    const bool lane0 = ln == 0;
    const int lrow0 = warp * 16 + g;
    const int grow0 = rb * 128 + lrow0;
    const uint32_t res = base + OFF_RES, trow = res + wg * 8192 + frag_offset(warp);
    uint32_t xr[32];
    float su0 = 0.f, su1 = 0.f, sq0 = 0.f, sq1 = 0.f, dt0 = 0.f, dt1 = 0.f;
    {
      const uint64_t da = make_desc(base + wg * 8192, 16, 1024), db = make_desc(base, 8192, 1024);
      constexpr int U = UNIT / 16;
#define HALF_STAGE(acc, xu, wu) _Pragma("unroll") for (int kk = 0; kk < 4; kk++) mma_ss<1>(acc, da + (xu) * U + kk * 2, db + (wu) * U + kk * 128, 1)
      PROF(10, ct == PT, 19); STAMP(0);
      cluster_arrive();
      mbar_wait(gfull, 1);
      mbar_wait(gfull + 8, 1);
      bar_sync(2 + wg, 256);
      wg_fence();
      HALF_STAGE(o, 6, 8);
      HALF_STAGE(o, 9, 11);
      wg_commit();
      STAMP(16);
      mbar_wait(gfull + 16, 1);
      STAMP(17);
      wg_fence();
      HALF_STAGE(o, 12, 1);
      wg_commit();
      bar_arrive(3 - wg, 256);
      mbar_wait(bar_par, 0);
      uint32_t* xo = g_xch + ((size_t)b * 8 * 256 + ct) * 4;
      const uint32_t* xi = g_xch + ((size_t)(b ^ 2) * 8 * 256 + ct) * 4;
      const uint32_t par1 = (~lds1(par + PAR_CONST + 4) & 1) << 16;
      wg_wait<0>();
      keep(o);
      mbar_arrive_pred(bar_ring, lane0);
      PROF(8, ct == PT, 20); STAMP(1);
#define SEND(i) st_b128(xo + (i) * 1024, (pack_bf(o[8 * (i)], o[8 * (i) + 1]) & ~0x10000u) | par1, pack_bf(o[8 * (i) + 2], o[8 * (i) + 3]), \
                        pack_bf(o[8 * (i) + 4], o[8 * (i) + 5]), pack_bf(o[8 * (i) + 6], o[8 * (i) + 7]))
#pragma unroll
      for (int i = 0; i < NS1; i++) SEND(i);
      PROF(8, ct == PT, 21); STAMP(2);
      bar_sync(2 + wg, 256);
      wg_fence();
      HALF_STAGE(s, 6, 7);
      HALF_STAGE(s, 9, 10);
      HALF_STAGE(s, 12, 0);
      wg_commit();
      bar_arrive(3 - wg, 256);
      STAMP(18);
      mbar_wait(gfull + 24, 1);
#pragma unroll
      for (int i = NS1; i < 8; i++) SEND(i);
      uint4 v[8];
#pragma unroll
      for (int i = 0; i < 4; i++) v[i] = ld_b128(xi + i * 1024);
      STAMP(19);
      mbar_wait(bar_rx, 0);
      wg_wait<0>();
      mbar_arrive_pred(bar_ring + 8, lane0);
      bar_sync(2 + wg, 256);
      STAMP(20);
#pragma unroll
      for (int i = 4; i < 8; i++) v[i] = ld_b128(xi + i * 1024);
      mbar_wait(bar_xres, 0);
      wg_fence();
      HALF_STAGE(s, 13, 2);
      HALF_STAGE(s, 8, 3);
      wg_commit();
      bar_arrive(3 - wg, 256);
      STAMP(21);
      wg_wait<0>();
      keep(s);
      mbar_arrive_pred(bar_ring + 16, lane0);
      PROF(10, ct == PT, 23); STAMP(4);
#pragma unroll
      for (int i = 0; i < 16; i += 2) ldmatrix4((trow ^ ((i & 7) << 4)) + (i >> 3) * 16384, xr[2 * i], xr[2 * i + 1], xr[2 * i + 2], xr[2 * i + 3]);
#pragma unroll
      for (int hf = 0; hf < 2; hf++) {
        uint32_t n = 0;
        bool ok;
        do {
          ok = true;
#pragma unroll
          for (int i = 4 * hf; i < 8; i++)
            if ((v[i].x & 0x10000u) != par1) { v[i] = ld_b128(xi + i * 1024); if (i < 4 * hf + 4) ok = false; }
          watchdog(n);
        } while (!ok);
        if (hf) { PROF(8, ct == PT, 22); STAMP(3); }
#pragma unroll
        for (int i = 8 * hf; i < 8 * hf + 8; i++) {
          const uint4 pv = lds4(par + PAR_T1 + i * 64 + tq * 16);
          const uint32_t w0 = (i & 1) ? v[i >> 1].z : v[i >> 1].x, w1 = (i & 1) ? v[i >> 1].w : v[i >> 1].y;
          const uint32_t u0 = hadd2(xr[2 * i], hmul2(pv.x, pack_bf(s[4 * i] + bf_lo(w0), s[4 * i + 1] + __uint_as_float(w0 & ((i & 1) ? 0xffff0000u : 0xfffe0000u)))));
          const uint32_t u1 = hadd2(xr[2 * i + 1], hmul2(pv.x, pack_bf(s[4 * i + 2] + bf_lo(w1), s[4 * i + 3] + bf_hi(w1))));
          xr[2 * i] = u0; xr[2 * i + 1] = u1;
          const float a = bf_lo(u0), c = bf_hi(u0), d = bf_lo(u1), e = bf_hi(u1);
          su0 += a + c; su1 += d + e;
          sq0 = fmaf(a, a, fmaf(c, c, sq0)); sq1 = fmaf(d, d, fmaf(e, e, sq1));
          dt0 = fmaf(a, __uint_as_float(pv.z), fmaf(c, __uint_as_float(pv.w), dt0));
          dt1 = fmaf(d, __uint_as_float(pv.z), fmaf(e, __uint_as_float(pv.w), dt1));
        }
      }
    }
    {
      const bool odd = tq & 1;
      float su = (odd ? su1 : su0) + __shfl_xor_sync(0xffffffffu, odd ? su0 : su1, 1);
      float sq = (odd ? sq1 : sq0) + __shfl_xor_sync(0xffffffffu, odd ? sq0 : sq1, 1);
      float dt = (odd ? dt1 : dt0) + __shfl_xor_sync(0xffffffffu, odd ? dt0 : dt1, 1);
      su += __shfl_xor_sync(0xffffffffu, su, 2); sq += __shfl_xor_sync(0xffffffffu, sq, 2); dt += __shfl_xor_sync(0xffffffffu, dt, 2);
      if (tq < 2) st_b128(g_stats + ((size_t)cj * SEQ + grow0 + tq * 8) * 4, __float_as_uint(su), __float_as_uint(sq), __float_as_uint(dt), tag);
    }
    PROF(8, ct == PT, 29); STAMP(5);
    uint32_t mm, ih, il;
    float rbest;
    {
      const uint32_t* sp = g_stats + ((size_t)(tq >> 1) * 4 * SEQ + grow0 + (tq & 1) * 8) * 4;
      uint4 v0 = ld_b128(sp), v1 = ld_b128(sp + SEQ * 4), v2 = ld_b128(sp + SEQ * 8), v3 = ld_b128(sp + SEQ * 12);
#pragma unroll
      for (int i = 0; i < 16; i += 2) stmatrix4((trow ^ ((i & 7) << 4)) + (i >> 3) * 16384, xr[2 * i], xr[2 * i + 1], xr[2 * i + 2], xr[2 * i + 3]);
      const uint4 cst = lds4(par + PAR_CONST);
      const float A1 = __uint_as_float(cst.x), A2 = __uint_as_float(cst.z);
      uint32_t n = 0;
      while (v0.w != tag || v1.w != tag || v2.w != tag || v3.w != tag) {
        if (v0.w != tag) v0 = ld_b128(sp);
        if (v1.w != tag) v1 = ld_b128(sp + SEQ * 4);
        if (v2.w != tag) v2 = ld_b128(sp + SEQ * 8);
        if (v3.w != tag) v3 = ld_b128(sp + SEQ * 12);
        watchdog(n);
      }
      __syncwarp();
      PROF(8, ct == PT, 30); STAMP(6);
      float su = (__uint_as_float(v0.x) + __uint_as_float(v1.x)) + (__uint_as_float(v2.x) + __uint_as_float(v3.x));
      float sq = (__uint_as_float(v0.y) + __uint_as_float(v1.y)) + (__uint_as_float(v2.y) + __uint_as_float(v3.y));
      float dt = (__uint_as_float(v0.z) + __uint_as_float(v1.z)) + (__uint_as_float(v2.z) + __uint_as_float(v3.z));
      su += __shfl_xor_sync(0xffffffffu, su, 2); sq += __shfl_xor_sync(0xffffffffu, sq, 2); dt += __shfl_xor_sync(0xffffffffu, dt, 2);
      const float m = su * (1.f / DM);
      float mb, sd;
      ln_scalars(m, fmaxf(sq * (1.f / DM) - m * m, 0.f), mb, sd);
      const float inv = rcp(sd);
      rbest = (dt - mb * A1) * inv + A2;
      mm = pack_bf(mb, mb);
      ih = pack_bf(inv, inv);
      const float lo = inv - bf_lo(ih);
      il = pack_bf(lo, lo);
    }
    int ibest;
    {
      const uint32_t bits = __float_as_uint(rbest) & ~3u, key = (int)bits < 0 ? ~bits : bits | 0x80000000u;
      const uint32_t kmax = __reduce_max_sync(0xffffffffu, key);
      const uint32_t row = __reduce_min_sync(0xffffffffu, key == kmax ? lrow0 + (tq & 1) * 8 : 255);
      if (lane0) sts2(par + PAR_RED + warp * 8, kmax, row);
      PROF(8, ct == PT, 38); STAMP(7);
      bar_sync(1, 256);
      const uint2 cv = lds2(par + PAR_RED + (ln & 7) * 8);
      const uint32_t k2 = __reduce_max_sync(0xffffffffu, cv.x);
      ibest = __reduce_min_sync(0xffffffffu, cv.x == k2 ? cv.y : 255);
      if (ct < 16) st_relaxed2(g_cand + (cj * 16 + ct) * 32 + rb * 2, (k2 & ~3u) | tag, ((rb * 128 + ibest) << 2) | tag);
    }
    PROF(8, ct == PT, 39); STAMP(8);
    if ((ibest >> 4) == warp) {
      const int src = (ibest & 7) * 4 + ((ibest >> 3) & 1), ch = g * 2;
      const uint32_t cm = __shfl_sync(0xffffffffu, mm, src), ch_ = __shfl_sync(0xffffffffu, ih, src), cl = __shfl_sync(0xffffffffu, il, src);
      const uint32_t xa = res + (ch >> 3) * 16384 + ibest * 128 + (((ch & 7) ^ (ibest & 7)) << 4) + tq * 4;
      const uint32_t x0 = lds1(xa), x1 = lds1(xa ^ 16);
      const uint2 p0 = lds2(par + PAR_T2 + ch * 32 + tq * 8), p1 = lds2(par + PAR_T2 + ch * 32 + 32 + tq * 8);
      uint32_t* dst = g_row + rb * 2 * DM + cj * 128 + ln * 4;
      st_pairs(dst, ln_mod(x0, cm, ch_, cl, p0.x, p0.y), ln_mod(x1, cm, ch_, cl, p1.x, p1.y), tag);
      st_pairs(dst + DM, x0, x1, tag);
      __syncwarp();
    }
    PROF(8, ct == PT, 37); STAMP(9);
    const uint32_t* inbox = g_cand + b * 32 + (ln & 15) * 2;
    uint2 cv = ld_relaxed2(inbox);
    uint32_t wf[128];
    const uint32_t frow = (ln & 7) + (ln >> 4) * 8;
    const uint32_t wfo = base + (warp & 1) * 8192 + frow * 64 + ((((ln >> 3) & 1) ^ ((frow >> 1) & 3)) << 4);
    if (b < NFFN) {
#pragma unroll
      for (int m = 0; m < 2; m++) {
        const uint32_t wfa = wfo + unit_of(m ? FT_U : FT_G, warp >> 1);
        mbar_wait(bar_box + (m * 4 + (warp >> 1)) * 8, 0);
#pragma unroll
        for (int f = 0; f < 16; f++) {
          const int r = ((f >> 1) * 4 + m * 2 + (f & 1)) * 4;
          ldmatrix4t((wfa ^ ((f & 1) * 32)) + (f >> 1) * 1024, wf[r], wf[r + 1], wf[r + 2], wf[r + 3]);
        }
      }
    }
    PROF(8, ct == PT, 31); STAMP(10);
    uint32_t kwin; int iwin;
    uint4 hv[8];
    uint32_t wd[64];
    const uint32_t wda = base + unit_of(FT_D, warp >> 1) + (warp & 1) * 8192 + frow * 128 + ((((ln >> 3) & 1) ^ (ln & 7)) << 4);
#define LOAD_WD(f) ldmatrix4t((wda ^ ((((f) >> 1) & 3) * 32)) + ((f) >> 3) * 4096 + ((f) & 1) * 2048, wd[4 * (f)], wd[4 * (f) + 1], wd[4 * (f) + 2], wd[4 * (f) + 3])
    {
      uint32_t n = 0;
      int cur = -1;
      while (true) {
        const bool valid = !(((cv.x ^ tag) | (cv.y ^ tag)) & 3u);
        const uint32_t key = valid ? cv.x : 0u;
        kwin = __reduce_max_sync(0xffffffffu, key);
        const int src = (__ffs(__ballot_sync(0xffffffffu, key == kwin)) - 1) & 15;
        if (kwin && src != cur) {
          cur = src;
#pragma unroll
          for (int i = 0; i < 8; i++) hv[i] = ld_pairs(g_row + cur * 2 * DM + warp * 128 + i * 16 + tq * 4);
        }
        if (__all_sync(0xffffffffu, valid)) break;
        cv = ld_relaxed2(inbox);
        watchdog(n);
      }
      iwin = __shfl_sync(0xffffffffu, cv.y, cur) >> 2;
    }
    PROF(8, ct == PT, 32); STAMP(11);
    const uint32_t* wrow = g_row + (iwin >> 7) * 2 * DM;
    if (b < NFFN) {
      {
        uint32_t n = 0;
        bool ok;
        do {
          ok = true;
#pragma unroll
          for (int i = 0; i < 8; i++)
            if (hv[i].y != tag || hv[i].w != tag) { hv[i] = ld_pairs(wrow + warp * 128 + i * 16 + tq * 4); ok = false; }
          watchdog(n);
        } while (!ok);
      }
      __syncwarp();
      PROF(8, ct == PT, 33); STAMP(12);
      float d[8][4];
#pragma unroll
      for (int i = 0; i < 8; i++) { d[i][0] = 0.f; d[i][1] = 0.f; d[i][2] = 0.f; d[i][3] = 0.f; }
#pragma unroll
      for (int ks = 0; ks < 8; ks++) {
#pragma unroll
        for (int mt = 0; mt < 4; mt++) {
          const int r = ks * 16 + mt * 4;
          mma16816(d[mt + (ks & 1) * 4], wf[r], wf[r + 1], wf[r + 2], wf[r + 3], hv[ks].x, hv[ks].z);
        }
        if (ks == 1) mbar_wait(bar_box + (8 + (warp >> 1)) * 8, 0);
        if (ks >= 1) {
#pragma unroll
          for (int f = 4 * ks - 4; f < 16 && f < 4 * ks; f++) LOAD_WD(f);
        }
      }
      if (tq == 0) {
        const uint32_t dst = base + unit_of(FT_G, warp >> 1) + (warp & 1) * 8192 + g * 32;
        sts4(dst, make_uint4(__float_as_uint(d[0][0] + d[4][0]), __float_as_uint(d[0][2] + d[4][2]), __float_as_uint(d[1][0] + d[5][0]), __float_as_uint(d[1][2] + d[5][2])));
        sts4(dst + 16, make_uint4(__float_as_uint(d[2][0] + d[6][0]), __float_as_uint(d[2][2] + d[6][2]), __float_as_uint(d[3][0] + d[7][0]), __float_as_uint(d[3][2] + d[7][2])));
      }
      bar_sync(1, 256);
      uint32_t ab[4];
      {
        float G = 0.f, U = 0.f;
        const uint32_t src = base + (ln & 7) * 32 + (ln >> 3) * 4;
#pragma unroll
        for (int w8 = 0; w8 < 8; w8++) {
          const uint32_t a = src + ((FT_G >> (w8 >> 1) * 4) & 15) * UNIT + (w8 & 1) * 8192;
          G += __uint_as_float(lds1(a)); U += __uint_as_float(lds1(a + 16));
        }
        const float act = rbf(silu_f(rbf(G))) * rbf(U);
        const uint32_t pk = pack_bf(act, __shfl_down_sync(0xffffffffu, act, 1));
#pragma unroll
        for (int i = 0; i < 4; i++) ab[i] = __shfl_sync(0xffffffffu, pk, i * 8 + tq * 2);
      }
      PROF(8, ct == PT, 34); STAMP(13);
#pragma unroll
      for (int mt = 0; mt < 8; mt++) {
        d[mt][0] = 0.f; d[mt][1] = 0.f; d[mt][2] = 0.f; d[mt][3] = 0.f;
        mma16816(d[mt], wd[mt * 8], wd[mt * 8 + 1], wd[mt * 8 + 2], wd[mt * 8 + 3], ab[0], ab[1]);
        mma16816(d[mt], wd[mt * 8 + 4], wd[mt * 8 + 5], wd[mt * 8 + 6], wd[mt * 8 + 7], ab[2], ab[3]);
      }
#pragma unroll
      for (int i = 0; i < 4; i++) {
        const int m4 = (i >> 1) * 4, e = (i & 1) * 2;
        const float y = (tq & 2) ? ((tq & 1) ? d[m4 + 3][e] : d[m4 + 2][e]) : ((tq & 1) ? d[m4 + 1][e] : d[m4][e]);
        st_relaxed(g_ypart + ((size_t)(warp * 16 + (m4 + tq) * 2 + (i & 1)) * NFFN + b) * 8 + g, tagf(y, tag));
      }
      PROF(8, ct == PT, 35); STAMP(14);
    }
    if (ct == 0) { sts2(par + PAR_CONST + 56, kwin, iwin); mbar_arrive(bar_win); }
    {
      const uint32_t mm0 = __shfl_sync(0xffffffffu, mm, ln & ~1), mm1 = __shfl_sync(0xffffffffu, mm, ln | 1);
      const uint32_t ih0 = __shfl_sync(0xffffffffu, ih, ln & ~1), ih1 = __shfl_sync(0xffffffffu, ih, ln | 1);
      const uint32_t il0 = __shfl_sync(0xffffffffu, il, ln & ~1), il1 = __shfl_sync(0xffffffffu, il, ln | 1);
      const bool mine = (iwin >> 4) == rb * 8 + warp;
#pragma unroll 1
      for (int hf = 0; hf < 2; hf++) {
        uint32_t x[16];
#pragma unroll
        for (int i = 0; i < 8; i += 2) ldmatrix4((trow ^ (i << 4)) + hf * 16384, x[2 * i], x[2 * i + 1], x[2 * i + 2], x[2 * i + 3]);
#pragma unroll
        for (int i = 0; i < 8; i++) {
          const uint2 pv = lds2(par + PAR_T2 + (hf * 8 + i) * 32 + tq * 8);
          const uint32_t gb = lds1(par + PAR_T1 + (hf * 8 + i) * 64 + tq * 16 + 4);
          x[2 * i] = hadd2(x[2 * i], hmul2(gb, ln_mod(x[2 * i], mm0, ih0, il0, pv.x, pv.y)));
          x[2 * i + 1] = hadd2(x[2 * i + 1], hmul2(gb, ln_mod(x[2 * i + 1], mm1, ih1, il1, pv.x, pv.y)));
        }
        if (mine) {
          uint32_t* dst = reinterpret_cast<uint32_t*>(P.out + (size_t)grow0 * DM + cj * 128 + hf * 64) + tq;
#pragma unroll
          for (int i = 0; i < 8; i++) {
            if (grow0 != iwin) dst[i * 4] = x[2 * i];
            if (grow0 + 8 != iwin) dst[i * 4 + 4 * DM] = x[2 * i + 1];
          }
        } else {
#pragma unroll
          for (int i = 0; i < 8; i += 2) stmatrix4((trow ^ (i << 4)) + hf * 16384, x[2 * i], x[2 * i + 1], x[2 * i + 2], x[2 * i + 3]);
          fence_async_smem();
          __syncwarp();
          if (elect_one()) {
            tma2d_store(&maps.out, res + hf * 16384 + warp * 2048, cj * 128 + hf * 64, rb * 128 + warp * 16);
            asm volatile("cp.async.bulk.commit_group;" ::: "memory");
          }
        }
      }
      asm volatile("cp.async.bulk.wait_group.read 0;" ::: "memory");
    }
    PROF(8, ct == PT, 11); STAMP(15);
    cluster_wait();
  }
}

typedef CUresult (*EncodeFn)(CUtensorMap*, CUtensorMapDataType, cuuint32_t, void*, const cuuint64_t*, const cuuint64_t*,
                             const cuuint32_t*, const cuuint32_t*, CUtensorMapInterleave, CUtensorMapSwizzle,
                             CUtensorMapL2promotion, CUtensorMapFloatOOBfill);

void map2d(EncodeFn enc, CUtensorMap* m, const void* p, uint64_t rows, uint64_t cols, uint32_t brows) {
  cuuint64_t dims[2] = {cols, rows}, strides[1] = {cols * 2};
  cuuint32_t box[2] = {64, brows}, es[2] = {1, 1};
  enc(m, CU_TENSOR_MAP_DATA_TYPE_BFLOAT16, 2, const_cast<void*>(p), dims, strides, box, es, CU_TENSOR_MAP_INTERLEAVE_NONE,
      CU_TENSOR_MAP_SWIZZLE_128B, CU_TENSOR_MAP_L2_PROMOTION_L2_256B, CU_TENSOR_MAP_FLOAT_OOB_FILL_NONE);
}
void map2d_narrow(EncodeFn enc, CUtensorMap* m, const void* p, uint64_t rows, uint64_t cols) {
  cuuint64_t dims[2] = {cols, rows}, strides[1] = {cols * 2};
  cuuint32_t box[2] = {32, 256}, es[2] = {1, 1};
  enc(m, CU_TENSOR_MAP_DATA_TYPE_BFLOAT16, 2, const_cast<void*>(p), dims, strides, box, es, CU_TENSOR_MAP_INTERLEAVE_NONE,
      CU_TENSOR_MAP_SWIZZLE_64B, CU_TENSOR_MAP_L2_PROMOTION_L2_64B, CU_TENSOR_MAP_FLOAT_OOB_FILL_NONE);
}
void map3d(EncodeFn enc, CUtensorMap* m, const void* p, uint64_t rows, uint64_t cols, uint32_t brows, uint32_t nch) {
  cuuint64_t dims[3] = {64, rows, cols / 64}, strides[2] = {cols * 2, 128};
  cuuint32_t box[3] = {64, brows, nch}, es[3] = {1, 1, 1};
  enc(m, CU_TENSOR_MAP_DATA_TYPE_BFLOAT16, 3, const_cast<void*>(p), dims, strides, box, es, CU_TENSOR_MAP_INTERLEAVE_NONE,
      CU_TENSOR_MAP_SWIZZLE_128B, CU_TENSOR_MAP_L2_PROMOTION_L2_256B, CU_TENSOR_MAP_FLOAT_OOB_FILL_NONE);
}

}

extern "C" void kernel_launch(void* const* d_in, const int* in_sizes, int n_in, void* d_out, int out_size) {
  (void)in_sizes; (void)n_in; (void)out_size;
  static EncodeFn enc = nullptr;
  if (!enc) {
    void* fn = nullptr;
    cudaDriverEntryPointQueryResult st;
    cudaGetDriverEntryPoint("cuTensorMapEncodeTiled", &fn, cudaEnableDefault, &st);
    enc = (EncodeFn)fn;
    cudaFuncSetAttribute(fused_kernel, cudaFuncAttributeMaxDynamicSharedMemorySize, SMEM_BYTES);
  }
  Maps maps;
  map2d(enc, &maps.x, d_in[0], SEQ, DM, 128);
  map2d(enc, &maps.out, d_out, SEQ, DM, 16);
  map3d(enc, &maps.wq, d_in[3], DM, NQ, 64, 2);
  map3d(enc, &maps.k, d_in[1], 4 * SK, 128, 128, 1);
  map3d(enc, &maps.v, d_in[2], 4 * SK, 128, 128, 1);
  map3d(enc, &maps.wo, d_in[4], NQ, DM, 64, 2);
  map2d_narrow(enc, &maps.wg, d_in[7], DM, FF);
  map2d_narrow(enc, &maps.wu, d_in[8], DM, FF);
  map3d(enc, &maps.wd, d_in[9], FF, DM, 32, 4);
  map2d_narrow(enc, &maps.wm, d_in[11], DM, NMOD);
  Ptrs p;
  p.x = (const __nv_bfloat16*)d_in[0];
  p.w_r = (const __nv_bfloat16*)d_in[6];
  p.w_gate = (const __nv_bfloat16*)d_in[7];
  p.w_up = (const __nv_bfloat16*)d_in[8];
  p.w_down = (const __nv_bfloat16*)d_in[9];
  p.c = (const __nv_bfloat16*)d_in[10];
  p.w_mod = (const __nv_bfloat16*)d_in[11];
  p.out = (__nv_bfloat16*)d_out;
  fused_kernel<<<NMAIN + NHELP, 384, SMEM_BYTES>>>(maps, p);
}
```

```cpp
#include <cuda_runtime.h>
#include <cuda_bf16.h>
#include <cuda.h>
#include <stdint.h>
#include <type_traits>

#define HD 1
#define HDX 2
#define XF 4
#define XE 32
#define XR 0
#define PF2 1
#define PF2T 1
#define NRS 6
#define FPACE 2
#define GOST 20
#define WB 2
#define WN 16
#define RES0 17
#define RES1 20
#define HU 32
#define NS1 4
#define VREL 7
#define E0 3

namespace {

constexpr int SEQ = 2048, DM = 1024, NQ = 4096, SK = 2048, WIN = 512, FF = 3584, NMOD = 6144;
constexpr int NMAIN = 128, NHELP = 4, NFFN = 112;
constexpr int NSLOT = 4, SLOT_BYTES = 32768, UNIT = 16384, GST_BYTES = 3 * UNIT;
constexpr uint32_t XT0 = 0x9630, XT1 = 0x54DC, XT2 = 0xDC96;
constexpr uint32_t WT0 = 0xA741, WT1 = 0x720A, WT2 = 0x20A7;
constexpr uint32_t AT0 = 0x7420, AT1 = 0x2C0A;
constexpr uint32_t QT = 0x549696DC;
constexpr int OFF_STAGE = 12 * UNIT;
constexpr uint32_t FT_G = 0x761B, FT_U = 0x0CA9, FT_D = 0x382D;
constexpr int OFF_RES = 4 * UNIT;
constexpr int OFF_PAR = 14 * UNIT;
constexpr int OFF_BAR = OFF_PAR + 2048 + 512;
constexpr int SMEM_BYTES = OFF_BAR + 512;
static_assert(SMEM_BYTES <= 232448, "smem");

constexpr int PAR_T1 = 0;
constexpr int PAR_T2 = 512;
constexpr int PAR_CONST = 1536;
constexpr int PAR_RED = 1600;
constexpr int PAR_SINK = 2176;

struct Maps {
  CUtensorMap x, wq, k, v, wo, wg, wu, wd, wm, out;
};
struct Ptrs {
  const __nv_bfloat16 *x, *w_r, *c, *w_mod, *w_gate, *w_up, *w_down;
  __nv_bfloat16* out;
};

__device__ __align__(1024) uint8_t g_act[16 * 80 * UNIT];
__device__ __align__(128) uint32_t g_mod[NMOD];
__device__ __align__(128) uint32_t g_modp[2 * 2 * DM];
__device__ __align__(128) uint32_t g_ln1[SEQ * 4];
__device__ __align__(128) uint32_t g_cnt_h[16 * 32];
__device__ __align__(128) uint32_t g_cnt_o[128 * 32];
__device__ __align__(128) uint32_t g_xch[NMAIN * 8 * 256 * 4];
__device__ __align__(128) uint32_t g_stats[8 * SEQ * 4];
__device__ __align__(128) uint32_t g_cand[NMAIN * 32];
__device__ __align__(128) uint32_t g_row[16 * 2 * DM];
__device__ __align__(128) uint32_t g_ypart[NMAIN * NFFN * 8];
__device__ uint32_t g_epoch;

__device__ __forceinline__ uint32_t fresh_lane() { uint32_t l; asm volatile("mov.u32 %0, %%laneid;" : "=r"(l)); return l; }
__device__ __forceinline__ uint32_t frag_offset(int warp) {
  const uint32_t l = fresh_lane();
  return ((warp & 3) * 16 + (l & 15)) * 128 + (((l >> 4) ^ (l & 7)) << 4);
}
__device__ __forceinline__ bool elect_one() {
  uint32_t p;
  asm volatile("{ .reg .pred q; elect.sync _|q, 0xffffffff; selp.u32 %0, 1, 0, q; }" : "=r"(p));
  return p;
}
__device__ __forceinline__ uint32_t smem_u32(const void* p) { return (uint32_t)__cvta_generic_to_shared(p); }
__device__ __forceinline__ void mbar_init(uint32_t bar, uint32_t cnt) {
  asm volatile("mbarrier.init.shared::cta.b64 [%0], %1;" ::"r"(bar), "r"(cnt) : "memory");
}
__device__ __forceinline__ void mbar_expect_tx(uint32_t bar, uint32_t bytes) {
  asm volatile("mbarrier.arrive.expect_tx.shared::cta.b64 _, [%0], %1;" ::"r"(bar), "r"(bytes) : "memory");
}
__device__ __forceinline__ void mbar_arrive(uint32_t bar) {
  asm volatile("mbarrier.arrive.shared::cta.b64 _, [%0];" ::"r"(bar) : "memory");
}
__device__ __forceinline__ void mbar_arrive_pred(uint32_t bar, bool p) {
  asm volatile("{ .reg .pred p; setp.ne.b32 p, %1, 0; @p mbarrier.arrive.shared::cta.b64 _, [%0]; }" ::"r"(bar), "r"((int)p) : "memory");
}
__device__ __forceinline__ void mbar_arrive_cl(uint32_t bar, uint32_t off, bool p = true) {
  asm volatile("{ .reg .pred p, q; .reg .b32 a; setp.ne.b32 q, %2, 0; setp.ne.and.b32 p, %0, 0, q; add.u32 a, %0, %1; @p mbarrier.arrive.shared::cluster.b64 _, [a]; }"
               ::"r"(bar), "r"(off), "r"((int)p) : "memory");
}
__device__ __forceinline__ uint32_t mapa(uint32_t addr, uint32_t cta) {
  uint32_t r; asm("mapa.shared::cluster.u32 %0, %1, %2;" : "=r"(r) : "r"(addr), "r"(cta)); return r;
}
__device__ __forceinline__ void cluster_arrive() { asm volatile("barrier.cluster.arrive.relaxed.aligned;" ::: "memory"); }
__device__ __forceinline__ void cluster_wait() { asm volatile("barrier.cluster.wait.aligned;" ::: "memory"); }
__device__ __forceinline__ void watchdog(uint32_t& n) {
}
__device__ __forceinline__ void mbar_wait(uint32_t bar, uint32_t parity) {
  asm volatile("{\n.reg .pred p;\nWAIT_%=:\nmbarrier.try_wait.parity.shared::cta.b64 p, [%0], %1;\n@!p bra WAIT_%=;\n}" ::"r"(bar), "r"(parity) : "memory");
}
__device__ __forceinline__ bool mbar_test(uint32_t bar, uint32_t parity) {
  uint32_t ok;
  asm volatile("{\n.reg .pred p;\nmbarrier.test_wait.parity.shared::cta.b64 p, [%1], %2;\nselp.u32 %0, 1, 0, p;\n}" : "=r"(ok) : "r"(bar), "r"(parity) : "memory");
  return ok;
}
__device__ __forceinline__ uint64_t l2_stream() {
  uint64_t f; asm("createpolicy.fractional.L2::evict_first.b64 %0, 1.0;" : "=l"(f)); return f;
}
__device__ __forceinline__ void tma2d(uint32_t dst, const CUtensorMap* m, int c0, int c1, uint32_t bar) {
  asm volatile("cp.async.bulk.tensor.2d.shared::cluster.global.mbarrier::complete_tx::bytes.L2::cache_hint [%0], [%1, {%3, %4}], [%2], %5;"
               ::"r"(dst), "l"(m), "r"(bar), "r"(c0), "r"(c1), "l"(l2_stream()) : "memory");
}
__device__ __forceinline__ void tma3d_prefetch(const CUtensorMap* m, int c0, int c1, int c2) {
  asm volatile("cp.async.bulk.prefetch.tensor.3d.L2.global.tile [%0, {%1, %2, %3}];" ::"l"(m), "r"(c0), "r"(c1), "r"(c2) : "memory");
}
__device__ __forceinline__ void bulk_load(uint32_t dst, const void* src, uint32_t bytes, uint32_t bar) {
  asm volatile("cp.async.bulk.shared::cluster.global.mbarrier::complete_tx::bytes [%0], [%1], %2, [%3];" ::"r"(dst), "l"(src), "r"(bytes), "r"(bar) : "memory");
}
__device__ __forceinline__ void bulk_load_stream(uint32_t dst, const void* src, uint32_t bytes, uint32_t bar) {
  asm volatile("cp.async.bulk.shared::cluster.global.mbarrier::complete_tx::bytes.L2::cache_hint [%0], [%1], %2, [%3], %4;"
               ::"r"(dst), "l"(src), "r"(bytes), "r"(bar), "l"(l2_stream()) : "memory");
}
__device__ __forceinline__ void tma2d_store(const CUtensorMap* m, uint32_t src, int c0, int c1) {
  asm volatile("cp.async.bulk.tensor.2d.global.shared::cta.bulk_group [%0, {%2, %3}], [%1];" ::"l"(m), "r"(src), "r"(c0), "r"(c1) : "memory");
}
__device__ __forceinline__ void bulk_store(void* dst, uint32_t src, uint32_t bytes) {
  asm volatile("cp.async.bulk.global.shared::cta.bulk_group [%0], [%1], %2;" ::"l"(dst), "r"(src), "r"(bytes) : "memory");
}
__device__ __forceinline__ uint32_t unit_of(uint32_t table, uint32_t i) { return ((table >> (i * 4)) & 15) * UNIT; }
__device__ __forceinline__ void tma3d(uint32_t dst, const CUtensorMap* m, int c0, int c1, int c2, uint32_t bar) {
  asm volatile("cp.async.bulk.tensor.3d.shared::cluster.global.mbarrier::complete_tx::bytes.L2::cache_hint [%0], [%1, {%3, %4, %5}], [%2], %6;"
               ::"r"(dst), "l"(m), "r"(bar), "r"(c0), "r"(c1), "r"(c2), "l"(l2_stream()) : "memory");
}
template <bool STREAM>
__device__ __forceinline__ void tma3d_mc(uint32_t dst, const CUtensorMap* m, int c0, int c1, int c2, uint32_t bar) {
  if (STREAM)
    asm volatile("cp.async.bulk.tensor.3d.shared::cluster.global.mbarrier::complete_tx::bytes.multicast::cluster.L2::cache_hint [%0], [%1, {%3, %4, %5}], [%2], %6, %7;"
                 ::"r"(dst), "l"(m), "r"(bar), "r"(c0), "r"(c1), "r"(c2), "h"((uint16_t)3), "l"(l2_stream()) : "memory");
  else
    asm volatile("cp.async.bulk.tensor.3d.shared::cluster.global.mbarrier::complete_tx::bytes.multicast::cluster [%0], [%1, {%3, %4, %5}], [%2], %6;"
                 ::"r"(dst), "l"(m), "r"(bar), "r"(c0), "r"(c1), "r"(c2), "h"((uint16_t)3) : "memory");
}
__device__ __forceinline__ void prefetch_map(const CUtensorMap* m) {
  asm volatile("prefetch.tensormap [%0];" ::"l"(m) : "memory");
}
__device__ __forceinline__ void fence_async() { asm volatile("fence.proxy.async.global;" ::: "memory"); }
__device__ __forceinline__ void fence_async_smem() { asm volatile("fence.proxy.async.shared::cta;" ::: "memory"); }
__device__ __forceinline__ void bar_sync(int id, int n) { asm volatile("bar.sync %0, %1;" ::"r"(id), "r"(n) : "memory"); }
__device__ __forceinline__ void bar_arrive(int id, int n) { asm volatile("bar.arrive %0, %1;" ::"r"(id), "r"(n) : "memory"); }
__device__ __forceinline__ void wg_fence() { asm volatile("wgmma.fence.sync.aligned;" ::: "memory"); }
__device__ __forceinline__ void wg_commit() { asm volatile("wgmma.commit_group.sync.aligned;" ::: "memory"); }
template <int N> __device__ __forceinline__ void wg_wait() { asm volatile("wgmma.wait_group.sync.aligned %0;" ::"n"(N) : "memory"); }
__device__ __forceinline__ uint64_t make_desc(uint32_t addr, uint32_t lbo, uint32_t sbo) {
  return (uint64_t)((addr & 0x3FFFF) >> 4) | ((uint64_t)(lbo >> 4) << 16) | ((uint64_t)(sbo >> 4) << 32) | (1ull << 62);
}
__device__ __forceinline__ uint32_t ld_relaxed(const uint32_t* p) {
  uint32_t v; asm volatile("ld.relaxed.gpu.global.u32 %0, [%1];" : "=r"(v) : "l"(p) : "memory"); return v;
}
__device__ __forceinline__ uint32_t ld_acquire(const uint32_t* p) {
  uint32_t v; asm volatile("ld.acquire.gpu.global.u32 %0, [%1];" : "=r"(v) : "l"(p) : "memory"); return v;
}
__device__ __forceinline__ uint4 ld_relaxed4(const uint32_t* p) {
  uint4 v; asm volatile("ld.relaxed.gpu.global.v4.u32 {%0,%1,%2,%3}, [%4];" : "=r"(v.x), "=r"(v.y), "=r"(v.z), "=r"(v.w) : "l"(p) : "memory"); return v;
}
__device__ __forceinline__ uint2 ld_relaxed2(const uint32_t* p) {
  uint2 v; asm volatile("ld.relaxed.gpu.global.v2.u32 {%0,%1}, [%2];" : "=r"(v.x), "=r"(v.y) : "l"(p) : "memory"); return v;
}
__device__ __forceinline__ void st_relaxed(uint32_t* p, uint32_t v) {
  asm volatile("st.relaxed.gpu.global.u32 [%0], %1;" ::"l"(p), "r"(v) : "memory");
}
__device__ __forceinline__ void st_relaxed2(uint32_t* p, uint32_t a, uint32_t b) {
  asm volatile("st.relaxed.gpu.global.v2.u32 [%0], {%1,%2};" ::"l"(p), "r"(a), "r"(b) : "memory");
}
__device__ __forceinline__ void st_relaxed4(uint32_t* p, uint32_t a, uint32_t b, uint32_t c, uint32_t d) {
  asm volatile("st.relaxed.gpu.global.v4.u32 [%0], {%1,%2,%3,%4};" ::"l"(p), "r"(a), "r"(b), "r"(c), "r"(d) : "memory");
}
__device__ __forceinline__ void st_b128(uint32_t* p, uint32_t a, uint32_t b, uint32_t c, uint32_t d) {
  asm volatile("{ .reg .b64 u, v; .reg .b128 w; mov.b64 u, {%1, %2}; mov.b64 v, {%3, %4}; mov.b128 w, {u, v}; st.relaxed.gpu.global.b128 [%0], w; }"
               ::"l"(p), "r"(a), "r"(b), "r"(c), "r"(d) : "memory");
}
__device__ __forceinline__ uint4 ld_b128(const uint32_t* p) {
  uint4 r;
  asm volatile("{ .reg .b64 u, v; .reg .b128 w; ld.relaxed.gpu.global.b128 w, [%4]; mov.b128 {u, v}, w; mov.b64 {%0, %1}, u; mov.b64 {%2, %3}, v; }"
               : "=r"(r.x), "=r"(r.y), "=r"(r.z), "=r"(r.w) : "l"(p) : "memory");
  return r;
}
__device__ __forceinline__ void st_pairs(uint32_t* p, uint32_t a, uint32_t b, uint32_t tag) {
  asm volatile("{ .reg .b64 u, v; mov.b64 u, {%1, %3}; mov.b64 v, {%2, %3}; st.relaxed.gpu.global.v2.b64 [%0], {u, v}; }"
               ::"l"(p), "r"(a), "r"(b), "r"(tag) : "memory");
}
__device__ __forceinline__ uint4 ld_pairs(const uint32_t* p) {
  uint4 v;
  asm volatile("{ .reg .b64 u, v; ld.relaxed.gpu.global.v2.b64 {u, v}, [%4]; mov.b64 {%0, %1}, u; mov.b64 {%2, %3}, v; }"
               : "=r"(v.x), "=r"(v.y), "=r"(v.z), "=r"(v.w) : "l"(p) : "memory");
  return v;
}
__device__ __forceinline__ uint2 ld_pair(const uint32_t* p) {
  uint2 v;
  asm volatile("{ .reg .b64 u; ld.relaxed.gpu.global.b64 u, [%2]; mov.b64 {%0, %1}, u; }" : "=r"(v.x), "=r"(v.y) : "l"(p) : "memory");
  return v;
}
__device__ __forceinline__ void red_release(uint32_t* p, uint32_t v) {
  asm volatile("red.release.gpu.global.add.u32 [%0], %1;" ::"l"(p), "r"(v) : "memory");
}
__device__ __forceinline__ uint32_t ldg_nc1(const void* p) {
  uint32_t v;
  asm volatile("ld.global.nc.u32 %0, [%1];" : "=r"(v) : "l"(p));
  return v;
}
__device__ __forceinline__ uint4 ldg_nc4(const void* p) {
  uint4 v; asm volatile("ld.global.nc.L1::no_allocate.v4.u32 {%0,%1,%2,%3}, [%4];" : "=r"(v.x), "=r"(v.y), "=r"(v.z), "=r"(v.w) : "l"(p)); return v;
}
__device__ __forceinline__ void stg4(void* p, uint4 v) {
  asm volatile("st.global.v4.u32 [%0], {%1,%2,%3,%4};" ::"l"(p), "r"(v.x), "r"(v.y), "r"(v.z), "r"(v.w) : "memory");
}
__device__ __forceinline__ void wait_counter(const uint32_t* p, uint32_t target) {
  uint32_t n = 0;
  while ((int)(ld_acquire(p) - target) < 0) { watchdog(n); }
}
__device__ __forceinline__ uint32_t tagf(float v, uint32_t tag) { return (__float_as_uint(v) & ~3u) | tag; }
__device__ __forceinline__ bool tag_ok(uint4 v, uint32_t tag) { return (((v.x ^ tag) | (v.y ^ tag) | (v.z ^ tag) | (v.w ^ tag)) & 3u) == 0; }
__device__ __forceinline__ float untag_sum(uint32_t a, uint32_t b) { return __uint_as_float(a & ~3u) + __uint_as_float(b & ~3u); }
__device__ __forceinline__ uint4 poll4(const uint32_t* p, uint32_t tag) {
  uint4 v = ld_relaxed4(p);
  uint32_t n = 0;
  while (!tag_ok(v, tag)) { v = ld_relaxed4(p); watchdog(n); }
  return v;
}
__device__ __forceinline__ float bf_lo(uint32_t v) { return __uint_as_float(v << 16); }
__device__ __forceinline__ float bf_hi(uint32_t v) { return __uint_as_float(v & 0xffff0000u); }
__device__ __forceinline__ uint32_t pack_bf(float lo, float hi) {
  uint32_t r; asm("cvt.rn.bf16x2.f32 %0, %1, %2;" : "=r"(r) : "f"(hi), "f"(lo)); return r;
}
__device__ __forceinline__ float rbf(float v) { return __uint_as_float(pack_bf(0.f, v) & 0xffff0000u); }
__device__ __forceinline__ uint32_t hmul2(uint32_t a, uint32_t b) {
  uint32_t r; asm("mul.rn.bf16x2 %0, %1, %2;" : "=r"(r) : "r"(a), "r"(b)); return r;
}
__device__ __forceinline__ uint32_t hadd2(uint32_t a, uint32_t b) {
  uint32_t r; asm("add.rn.bf16x2 %0, %1, %2;" : "=r"(r) : "r"(a), "r"(b)); return r;
}
__device__ __forceinline__ uint32_t hsub2(uint32_t a, uint32_t b) {
  uint32_t r; asm("sub.rn.bf16x2 %0, %1, %2;" : "=r"(r) : "r"(a), "r"(b)); return r;
}
__device__ __forceinline__ uint32_t hmax2(uint32_t a, uint32_t b) {
  uint32_t r; asm("max.bf16x2 %0, %1, %2;" : "=r"(r) : "r"(a), "r"(b)); return r;
}
__device__ __forceinline__ float rcp(float x) { float r; asm("rcp.approx.ftz.f32 %0, %1;" : "=f"(r) : "f"(x)); return r; }
__device__ __forceinline__ float ex2(float x) { float r; asm("ex2.approx.ftz.f32 %0, %1;" : "=f"(r) : "f"(x)); return r; }
__device__ __forceinline__ void stmatrix4(uint32_t addr, uint32_t a, uint32_t b, uint32_t c, uint32_t d) {
  asm volatile("stmatrix.sync.aligned.m8n8.x4.shared.b16 [%0], {%1,%2,%3,%4};" ::"r"(addr), "r"(a), "r"(b), "r"(c), "r"(d) : "memory");
}
__device__ __forceinline__ void ldmatrix4(uint32_t addr, uint32_t& a, uint32_t& b, uint32_t& c, uint32_t& d) {
  asm volatile("ldmatrix.sync.aligned.m8n8.x4.shared.b16 {%0,%1,%2,%3}, [%4];" : "=r"(a), "=r"(b), "=r"(c), "=r"(d) : "r"(addr) : "memory");
}
__device__ __forceinline__ void ldmatrix4t(uint32_t addr, uint32_t& a, uint32_t& b, uint32_t& c, uint32_t& d) {
  asm volatile("ldmatrix.sync.aligned.m8n8.x4.trans.shared.b16 {%0,%1,%2,%3}, [%4];" : "=r"(a), "=r"(b), "=r"(c), "=r"(d) : "r"(addr) : "memory");
}
__device__ __forceinline__ void mma16816(float (&d)[4], uint32_t a0, uint32_t a1, uint32_t a2, uint32_t a3, uint32_t b0, uint32_t b1) {
  asm volatile("mma.sync.aligned.m16n8k16.row.col.f32.bf16.bf16.f32 {%0,%1,%2,%3}, {%4,%5,%6,%7}, {%8,%9}, {%0,%1,%2,%3};"
               : "+f"(d[0]), "+f"(d[1]), "+f"(d[2]), "+f"(d[3]) : "r"(a0), "r"(a1), "r"(a2), "r"(a3), "r"(b0), "r"(b1));
}
__device__ __forceinline__ void sts1(uint32_t a, uint32_t v) { asm volatile("st.shared.u32 [%0], %1;" ::"r"(a), "r"(v) : "memory"); }
__device__ __forceinline__ uint4 lds4(uint32_t a) {
  uint4 v; asm volatile("ld.shared.v4.u32 {%0,%1,%2,%3}, [%4];" : "=r"(v.x), "=r"(v.y), "=r"(v.z), "=r"(v.w) : "r"(a) : "memory"); return v;
}
__device__ __forceinline__ uint2 lds2(uint32_t a) {
  uint2 v; asm volatile("ld.shared.v2.u32 {%0,%1}, [%2];" : "=r"(v.x), "=r"(v.y) : "r"(a) : "memory"); return v;
}
__device__ __forceinline__ uint32_t lds1(uint32_t a) {
  uint32_t v; asm volatile("ld.shared.u32 %0, [%1];" : "=r"(v) : "r"(a) : "memory"); return v;
}
__device__ __forceinline__ void sts2(uint32_t a, uint32_t x, uint32_t y) { asm volatile("st.shared.v2.u32 [%0], {%1,%2};" ::"r"(a), "r"(x), "r"(y) : "memory"); }
__device__ __forceinline__ void sts4(uint32_t a, uint4 v) {
  asm volatile("st.shared.v4.u32 [%0], {%1,%2,%3,%4};" ::"r"(a), "r"(v.x), "r"(v.y), "r"(v.z), "r"(v.w) : "memory");
}
__device__ __forceinline__ float silu_f(float v) { return __fdividef(v, 1.f + __expf(-v)); }
__device__ __forceinline__ uint32_t hfma2(uint32_t a, uint32_t b, uint32_t c) {
  uint32_t r; asm("fma.rn.bf16x2 %0, %1, %2, %3;" : "=r"(r) : "r"(a), "r"(b), "r"(c)); return r;
}
__device__ __forceinline__ void split_inv(float sd, uint32_t& ih, uint32_t& il) {
  const float inv = rcp(sd);
  ih = pack_bf(inv, inv);
  const float lo = inv - bf_lo(ih);
  il = pack_bf(lo, lo);
}
__device__ __forceinline__ uint32_t ln_mod(uint32_t x, uint32_t mean2, uint32_t ih, uint32_t il, uint32_t c1, uint32_t sh) {
  const uint32_t d = hsub2(x, mean2);
  return hadd2(hmul2(hfma2(d, ih, hmul2(d, il)), c1), sh);
}

#define R8(a, i) "+f"(a[i]), "+f"(a[i + 1]), "+f"(a[i + 2]), "+f"(a[i + 3]), "+f"(a[i + 4]), "+f"(a[i + 5]), "+f"(a[i + 6]), "+f"(a[i + 7])
#define D64 "{%0,%1,%2,%3,%4,%5,%6,%7,%8,%9,%10,%11,%12,%13,%14,%15,%16,%17,%18,%19,%20,%21,%22,%23,%24,%25,%26,%27,%28,%29,%30,%31," \
            "%32,%33,%34,%35,%36,%37,%38,%39,%40,%41,%42,%43,%44,%45,%46,%47,%48,%49,%50,%51,%52,%53,%54,%55,%56,%57,%58,%59,%60,%61,%62,%63}"
template <int TB>
__device__ __forceinline__ void mma_ss(float (&d)[64], uint64_t da, uint64_t db, int sc) {
  asm volatile("{\n.reg .pred p;\nsetp.ne.b32 p, %66, 0;\n"
               "wgmma.mma_async.sync.aligned.m64n128k16.f32.bf16.bf16 " D64 ", %64, %65, p, 1, 1, 0, %67;\n}"
               : R8(d, 0), R8(d, 8), R8(d, 16), R8(d, 24), R8(d, 32), R8(d, 40), R8(d, 48), R8(d, 56)
               : "l"(da), "l"(db), "r"(sc), "n"(TB));
}
template <int TB>
__device__ __forceinline__ void mma_rs(float (&d)[64], uint32_t a0, uint32_t a1, uint32_t a2, uint32_t a3, uint64_t db, int sc) {
  asm volatile("{\n.reg .pred p;\nsetp.ne.b32 p, %69, 0;\n"
               "wgmma.mma_async.sync.aligned.m64n128k16.f32.bf16.bf16 " D64 ", {%64,%65,%66,%67}, %68, p, 1, 1, %70;\n}"
               : R8(d, 0), R8(d, 8), R8(d, 16), R8(d, 24), R8(d, 32), R8(d, 40), R8(d, 48), R8(d, 56)
               : "r"(a0), "r"(a1), "r"(a2), "r"(a3), "l"(db), "r"(sc), "n"(TB));
}
#define D128 "{%0,%1,%2,%3,%4,%5,%6,%7,%8,%9,%10,%11,%12,%13,%14,%15,%16,%17,%18,%19,%20,%21,%22,%23,%24,%25,%26,%27,%28,%29,%30,%31," \
             "%32,%33,%34,%35,%36,%37,%38,%39,%40,%41,%42,%43,%44,%45,%46,%47,%48,%49,%50,%51,%52,%53,%54,%55,%56,%57,%58,%59,%60,%61,%62,%63," \
             "%64,%65,%66,%67,%68,%69,%70,%71,%72,%73,%74,%75,%76,%77,%78,%79,%80,%81,%82,%83,%84,%85,%86,%87,%88,%89,%90,%91,%92,%93,%94,%95," \
             "%96,%97,%98,%99,%100,%101,%102,%103,%104,%105,%106,%107,%108,%109,%110,%111,%112,%113,%114,%115,%116,%117,%118,%119,%120,%121,%122,%123,%124,%125,%126,%127}"
#define R128(d, e) R8(d, 0), R8(d, 8), R8(d, 16), R8(d, 24), R8(d, 32), R8(d, 40), R8(d, 48), R8(d, 56), \
                   R8(e, 0), R8(e, 8), R8(e, 16), R8(e, 24), R8(e, 32), R8(e, 40), R8(e, 48), R8(e, 56)
__device__ __forceinline__ void mma256_ss(float (&d)[64], float (&e)[64], uint64_t da, uint64_t db, int sc) {
  asm volatile("{\n.reg .pred p;\nsetp.ne.b32 p, %130, 0;\n"
               "wgmma.mma_async.sync.aligned.m64n256k16.f32.bf16.bf16 " D128 ", %128, %129, p, 1, 1, 0, 1;\n}"
               : R128(d, e) : "l"(da), "l"(db), "r"(sc));
}
__device__ __forceinline__ void mma256_rs(float (&d)[64], float (&e)[64], uint32_t a0, uint32_t a1, uint32_t a2, uint32_t a3, uint64_t db) {
  asm volatile("{\n.reg .pred p;\nsetp.ne.b32 p, 1, 0;\n"
               "wgmma.mma_async.sync.aligned.m64n256k16.f32.bf16.bf16 " D128 ", {%128,%129,%130,%131}, %132, p, 1, 1, 1;\n}"
               : R128(d, e) : "r"(a0), "r"(a1), "r"(a2), "r"(a3), "l"(db));
}
template <int N> __device__ __forceinline__ void keep(float (&a)[N]) {
#pragma unroll
  for (int i = 0; i < N; i++) asm volatile("" : "+f"(a[i])::"memory");
}
template <int N> __device__ __forceinline__ void keep(uint32_t (&a)[N]) {
#pragma unroll
  for (int i = 0; i < N; i++) asm volatile("" : "+r"(a[i])::"memory");
}

#define STAMP(idx) do {} while (0)
#define PROF(grp, cond, idx) do {} while (0)

constexpr float SCL2 = 1.4426950408889634f * 0.08838834764831845f;

__device__ __forceinline__ void pack_p(const float (&s)[64], uint32_t (&p)[32]) {
#pragma unroll
  for (int i = 0; i < 32; i++) p[i] = pack_bf(s[2 * i], s[2 * i + 1]);
}

__device__ __forceinline__ void issue_qk(float (&s)[64], uint32_t q0, uint32_t q1, uint32_t kslot) {
  const uint64_t db = make_desc(kslot, 16, 1024), da0 = make_desc(q0, 16, 1024), da1 = make_desc(q1, 16, 1024);
#pragma unroll
  for (int kk = 0; kk < 8; kk++) mma_ss<0>(s, (kk < 4 ? da0 : da1) + (kk & 3) * 2, db + (kk >> 2) * 1024 + (kk & 3) * 2, kk != 0);
}
__device__ __forceinline__ void issue_pv(float (&o)[64], uint32_t (&p)[32], uint32_t vslot, int acc) {
  uint64_t db = make_desc(vslot, 16384, 1024);
#pragma unroll
  for (int kk = 0; kk < 8; kk++)
    mma_rs<1>(o, p[4 * kk], p[4 * kk + 1], p[4 * kk + 2], p[4 * kk + 3], db + kk * 128, kk == 0 ? acc : 1);
}

template <int H>
__device__ __forceinline__ void store_chunk(const float (&a)[64], uint32_t addr) {
#pragma unroll
  for (int i = 8 * H; i < 8 * H + 8; i += 2)
    stmatrix4(addr ^ ((i & 7) << 4), pack_bf(a[4 * i], a[4 * i + 1]), pack_bf(a[4 * i + 2], a[4 * i + 3]),
              pack_bf(a[4 * i + 4], a[4 * i + 5]), pack_bf(a[4 * i + 6], a[4 * i + 7]));
}
template <int H>
__device__ __forceinline__ void store_chunk(const float (&a)[64], float i0, float i1, uint32_t addr) {
#pragma unroll
  for (int i = 8 * H; i < 8 * H + 8; i += 2)
    stmatrix4(addr ^ ((i & 7) << 4), pack_bf(a[4 * i] * i0, a[4 * i + 1] * i0), pack_bf(a[4 * i + 2] * i1, a[4 * i + 3] * i1),
              pack_bf(a[4 * i + 4] * i0, a[4 * i + 5] * i0), pack_bf(a[4 * i + 6] * i1, a[4 * i + 7] * i1));
}
__device__ __forceinline__ float inv_quad_sum(float l) {
  l += __shfl_xor_sync(0xffffffffu, l, 1);
  l += __shfl_xor_sync(0xffffffffu, l, 2);
  return rcp(l);
}

__device__ __forceinline__ void ln_scalars(float mean, float var, float& mb, float& sd) {
  mb = rbf(mean);
  float r; asm("sqrt.approx.ftz.f32 %0, %1;" : "=f"(r) : "f"(rbf(rbf(var) + 1e-5f)));
  sd = rbf(r);
}

__global__ void __cluster_dims__(2, 1, 1) __launch_bounds__(384, 1) fused_kernel(const __grid_constant__ Maps maps, const Ptrs P) {
  extern __shared__ __align__(1024) uint8_t smem_raw[];
  const uint32_t base = smem_u32(smem_raw);
  const int tid = threadIdx.x, lane = tid & 31;
  const int warp = __shfl_sync(0xffffffffu, tid >> 5, 0);
  const int b = blockIdx.x;
  PROF(31, tid == 0, 0);

  if (b >= NMAIN) {
    float* sc = reinterpret_cast<float*>(smem_raw);
    float* red = sc + DM;
    for (int k = tid; k < DM; k += 384) sc[k] = rbf(silu_f(__bfloat162float(P.c[k])));
    __syncthreads();
    if (tid < 256) {
      const int col = 2048 + (b - NMAIN) * 1024 + (tid & 127) * 8, r0 = (tid >> 7) * 512;
      float acc[8];
#pragma unroll
      for (int e = 0; e < 8; e++) acc[e] = 0.f;
#pragma unroll 1
      for (int r = r0; r < r0 + 512; r += HU) {
        uint4 w[HU];
#pragma unroll
        for (int u = 0; u < HU; u++) w[u] = ldg_nc4(P.w_mod + (size_t)(r + u) * NMOD + col);
#pragma unroll
        for (int u = 0; u < HU; u++) {
          float s = sc[r + u];
          acc[0] += s * bf_lo(w[u].x); acc[1] += s * bf_hi(w[u].x); acc[2] += s * bf_lo(w[u].y); acc[3] += s * bf_hi(w[u].y);
          acc[4] += s * bf_lo(w[u].z); acc[5] += s * bf_hi(w[u].z); acc[6] += s * bf_lo(w[u].w); acc[7] += s * bf_hi(w[u].w);
        }
      }
      if (tid >= 128) {
#pragma unroll
        for (int e = 0; e < 8; e++) red[(tid & 127) * 8 + e] = acc[e];
      }
      const uint32_t tag = ld_relaxed(&g_epoch) % 3 + 1;
      bar_sync(1, 256);
      if (tid < 128) {
        uint32_t o[8];
#pragma unroll
        for (int e = 0; e < 8; e++) o[e] = __float_as_uint(rbf(acc[e] + red[tid * 8 + e])) | tag;
        st_relaxed4(g_mod + col, o[0], o[1], o[2], o[3]);
        st_relaxed4(g_mod + col + 4, o[4], o[5], o[6], o[7]);
        const uint4 wr = ldg_nc4(P.w_r + tid * 8);
        const uint32_t wv[4] = {wr.x, wr.y, wr.z, wr.w};
        float dsum = 0.f;
#pragma unroll
        for (int e = 0; e < 8; e++) {
          const float m = bf_hi(o[e]);
          dsum += (b == NMAIN + 2 ? rbf(1.f + m) : m) * ((e & 1) ? bf_hi(wv[e >> 1]) : bf_lo(wv[e >> 1]));
        }
#pragma unroll
        for (int k = 16; k > 0; k >>= 1) dsum += __shfl_xor_sync(0xffffffffu, dsum, k);
        if (lane == 0) st_relaxed(g_mod + (b - NMAIN) * 4 + warp, tagf(dsum, tag));
      }
    }
    PROF(2, tid == 0, 1);
    return;
  }

  const int rank = b & 1;
  const int rb = ((b >> 4) << 1) | rank, cj = (b >> 1) & 7;
  const uint32_t bfull = base + OFF_BAR, bempty = bfull + NSLOT * 8;
  const uint32_t gfull = bempty + NSLOT * 8, gempty = gfull + 32;
  const uint32_t bar_ofull = gempty + 32;
  const uint32_t bar_ofree = bar_ofull + 16;
  const uint32_t bar_par = bar_ofree + 32;
  const uint32_t bar_mod = bar_par + 8;
  const uint32_t bar_pread = bar_mod + 8;
  const uint32_t bar_xres = bar_pread + 8;
  const uint32_t bar_ring = bar_xres + 8;
  const uint32_t bar_box = bar_ring + 24;
  const uint32_t bar_go = bar_box + 96;
  const uint32_t bar_go2 = bar_go + 16;
  const uint32_t bar_cnt = bar_go + 24;
  const uint32_t xfull = bar_go + 32, xempty = xfull + 32;
  const uint32_t bar_hw = xempty + 32, bar_hx = bar_hw + 8;
  const uint32_t bar_hpub = bar_hx + 16;
  const uint32_t bar_win = bar_hpub + 8;
  const uint32_t bar_rx = bar_win + 8;
  const uint32_t bar_res = bar_go + 8;
  const uint32_t stage = base + OFF_STAGE, par = base + OFF_PAR;

  if (warp == 8 && elect_one()) {
    for (int s = 0; s < NSLOT; s++) { mbar_init(bfull + s * 8, 1); mbar_init(bempty + s * 8, 16); }
    for (int s = 0; s < 4; s++) { mbar_init(gfull + s * 8, 1); mbar_init(gempty + s * 8, 16); mbar_init(xfull + s * 8, 1); mbar_init(xempty + s * 8, 8); mbar_init(bar_ofree + s * 8, 1); }
    mbar_init(bar_ofull, 128); mbar_init(bar_ofull + 8, 128);
    mbar_init(bar_par, 64); mbar_init(bar_mod, 256); mbar_init(bar_pread, 8); mbar_init(bar_xres, 1);
    mbar_init(bar_ring, 8); mbar_init(bar_ring + 8, 8); mbar_init(bar_ring + 16, 8);
    mbar_init(bar_go, 1); mbar_init(bar_go2, 1); mbar_init(bar_cnt, 1); mbar_init(bar_hpub, 8); mbar_init(bar_res, 1); mbar_init(bar_win, 1); mbar_init(bar_rx, 1);
    for (int s = 0; s < 12; s++) mbar_init(bar_box + s * 8, 1);
    asm volatile("fence.mbarrier_init.release.cluster;" ::: "memory");
    prefetch_map(&maps.x); prefetch_map(&maps.wq); prefetch_map(&maps.k); prefetch_map(&maps.v);
  }
  if (warp == 9 && elect_one()) {
    mbar_init(bar_hw, 1); mbar_init(bar_hx, 1); mbar_init(bar_hx + 8, 1);
    asm volatile("fence.mbarrier_init.release.cluster;" ::: "memory");
    mbar_expect_tx(bar_hw, 32768);
    mbar_expect_tx(bar_hx, 16384);
    mbar_expect_tx(bar_hx + 8, 16384);
    const __nv_bfloat16* xs = P.x + (size_t)(rb * 128 + cj * 16) * DM;
    bulk_load(base + 2 * GST_BYTES, xs, 16384, bar_hx);
    tma2d(stage, &maps.wm, (b >> 1) * 32, rank * 512, bar_hw);
    tma2d(stage + 16384, &maps.wm, (b >> 1) * 32, rank * 512 + 256, bar_hw);
    bulk_load(base + 3 * GST_BYTES, xs + 8 * DM, 16384, bar_hx + 8);
  }
  cluster_arrive();

  if (warp >= 8) {
    asm volatile("setmaxnreg.dec.sync.aligned.u32 40;");
    if (warp < 10) bar_arrive(1, 320);
    const uint32_t epoch = ld_relaxed(&g_epoch);
    cluster_wait();
    if (warp == 8) {
      const int kvrow = (cj >> 1) * SK + (SK - WIN);
      int wch = cj * 8 + rank * 2;
#pragma unroll 1
      for (int ps = 0; ps < 3; ps++) {
        const CUtensorMap* mw = ps == 2 ? &maps.wo : &maps.wq;
        const uint32_t xt = ps == 1 ? XT1 : XT2, wt = ps == 0 ? WT0 : (ps == 1 ? WT1 : WT2);
        const int nst = ps == 2 ? 32 : 16;
        if (ps) {
          mbar_wait(bar_ofree + (ps - 1) * 16, 0);
          fence_async();
        }
#pragma unroll 1
        for (int i = 0; i < nst; i++) {
          const uint32_t bf = gfull + (i & 3) * 8;
          const int kt = ps == 2 ? (((cj & 1) * 4 + ((i >> 1) & 3)) * 4 + (i >> 3)) * 2 + (i & 1) : (i + (ps ? 0 : b & 14)) & 15;
          const uint32_t wd = base + unit_of(wt, i & 3) + rank * UNIT, xd = base + unit_of(xt, i & 3);
          const uint8_t* xs = g_act + (uint32_t)(rb * 80 + (ps - 1) * 16 + kt) * UNIT;
          if (ps == 0 && i == HD) mbar_wait(bar_mod, 0);
          if (ps && i && i < 4) mbar_wait(bempty + (i == 3 ? 3 : i - 1) * 8, 1);
          mbar_wait(gempty + (i & 3) * 8, ((i >> 2) & 1) ^ 1);
          if (elect_one()) {
            mbar_expect_tx(bf, ps ? GST_BYTES : 2 * UNIT);
            tma3d_mc<true>(wd, mw, 0, (i == 31 ? kt ^ (rank * 32) : kt) * 64, i == 31 ? cj * 2 : wch, bf);
          }
          if (ps) {
            if (i == 16) mbar_wait(bar_cnt, 0);
            if (i == 2) mbar_wait(bempty + 16, 1);
            if (elect_one()) {
              bulk_load_stream(xd, xs, UNIT, bf);
              mbar_arrive_pred(ps == 1 ? bar_go2 : bar_go, i == (ps == 1 ? 15 : GOST - 1));
              mbar_arrive_pred(bar_res, ((1u << RES0 | 1u << RES1) >> i) & 1);
            }
          }
        }
        if (ps == 2) break;
        wch = ps ? ((wch >> 3) ^ rank) * 2 : wch + 4;
#pragma unroll 1
        for (int u = 0; u < 16; u++) {
          const bool isk = (u == 0) || ((u & 1) && u < 15);
          const int blk = (isk ? (u + 1) >> 1 : (u == 15 ? 7 : (u >> 1) - 1)) & 3;
          const uint32_t sl = base + unit_of(ps ? AT1 : AT0, u & 3) + rank * UNIT, bf = bfull + (u & 3) * 8;
          if (u < 4) mbar_wait(gempty + ((u + 1) >> 1) * 8, 1);
          mbar_wait(bempty + (u & 3) * 8, ((u >> 2) & 1) ^ 1);
          if (elect_one()) {
            mbar_expect_tx(bf, SLOT_BYTES);
            tma3d_mc<false>(sl, isk ? &maps.k : &maps.v, 0, kvrow + blk * 128, rank, bf);
          }
        }
      }
      mbar_wait(bar_ring, 0);
      if (elect_one()) {
        mbar_expect_tx(bar_rx, UNIT);
        bulk_load_stream(base + 8 * UNIT, g_act + (uint32_t)(rb * 80 + 16 + 63 - (cj & 1) * 32) * UNIT, UNIT, bar_rx);
      }
      if (b < NFFN) {
#pragma unroll 1
        for (int u = 0; u < 12; u++) {
          if (u == 2 || u == 8) mbar_wait(bar_ring + 8 + (u & 8), 0);
          if (u >= FPACE) mbar_wait(bar_box + (u - FPACE) * 8, 0);
          const uint32_t dst = base + unit_of(u < 4 ? FT_G : (u < 8 ? FT_U : FT_D), u & 3);
          if (elect_one()) {
            mbar_expect_tx(bar_box + u * 8, UNIT);
            if (u < 8) tma2d(dst, u < 4 ? &maps.wg : &maps.wu, b * 32, (u & 3) * 256, bar_box + u * 8);
            else tma3d(dst, &maps.wd, 0, b * 32, (u - 8) * 4, bar_box + u * 8);
          }
        }
      }
    } else if (warp == 9) {
      const uint32_t target = 8 * (epoch + 1);
#pragma unroll 1
      for (int i = 0; i < 16; i++) {
        if (i == HDX) mbar_wait(bar_mod, 0);
        if (i == NRS) {
          wait_counter(&g_cnt_h[rb * 32], target);
          PROF(1, lane == 0, 26);
          fence_async();
        }
        mbar_wait(xempty + (i & 3) * 8, ((i >> 2) & 1) ^ 1);
        if (elect_one()) {
          mbar_expect_tx(xfull + (i & 3) * 8, UNIT);
          if (i < NRS) tma2d(base + (i & 3) * GST_BYTES, &maps.x, ((2 * cj + i) & 15) * 64, rb * 128, xfull + (i & 3) * 8);
          else bulk_load_stream(base + (i & 3) * GST_BYTES, g_act + (uint32_t)(rb * 80 + ((2 * cj + i) & 15)) * UNIT, UNIT, xfull + (i & 3) * 8);
        }
      }
      prefetch_map(&maps.wo);
#pragma unroll 1
      for (int t = 0; t < 4; t++) {
#pragma unroll 1
        for (int w = 0; w < 2; w++) {
          mbar_wait(bar_ofull + w * 8, t & 1);
          uint8_t* dst = g_act + (uint32_t)(rb * 80 + 16 + (cj * 4 + t) * 2) * UNIT + w * 8192;
          if (elect_one()) {
            bulk_store(dst, base + unit_of(QT, 2 * t) + w * 8192, 8192);
            bulk_store(dst + UNIT, base + unit_of(QT, 2 * t + 1) + w * 8192, 8192);
            asm volatile("cp.async.bulk.commit_group;" ::: "memory");
          }
        }
        if (elect_one()) {
          asm volatile("cp.async.bulk.wait_group.read 0;" ::: "memory");
          mbar_arrive(bar_ofree + t * 8);
          asm volatile("cp.async.bulk.wait_group 0;" ::: "memory");
          fence_async();
          red_release(&g_cnt_o[((rb * 4 + t) * 2 + (cj >> 2)) * 32], 2);
          if (t == PF2T) for (int u = 0; u < PF2; u++)
            tma3d_prefetch(&maps.wo, 0, ((((cj & 1) * 4 + (b >> 5)) * 4 + u) * 2 + ((b >> 4) & 1)) * 64, (cj ^ rank) * 2);
        }
        if (t & 1) {
          wait_counter(&g_cnt_o[(rb * 8 + 2 * t - 2 + (cj & 1)) * 32], target);
          wait_counter(&g_cnt_o[(rb * 8 + 2 * t + (cj & 1)) * 32], target);
        }
      }
      wait_counter(&g_cnt_o[(rb * 8 + 7 - (cj & 1)) * 32], target);
      fence_async();
      if (elect_one()) {
        mbar_arrive(bar_cnt);
        PROF(2, true, 27);
        mbar_expect_tx(bar_xres, 32768);
      }
#pragma unroll 1
      for (int u = 0; u < 2; u++) {
        mbar_wait(bar_res, u);
        if (elect_one()) tma2d(base + OFF_RES + u * UNIT, &maps.x, cj * 128 + u * 64, rb * 128, bar_xres);
      }
    } else {
      const int t2 = tid - 320;
      if (t2 == 0) {
        mbar_wait(bar_hpub, 0);
        PROF(1, true, 24);
        red_release(&g_cnt_h[rb * 32], 1);
        PROF(1, true, 25);
        prefetch_map(&maps.wg); prefetch_map(&maps.wu); prefetch_map(&maps.wd); prefetch_map(&maps.out);
      }
      __syncwarp();
      if (b < NFFN) {
        mbar_wait(bar_go2, 0);
        const __nv_bfloat16* pg = ((b & 1) ? P.w_up : P.w_gate) + (b >> 1) * 64 + (size_t)t2 * FF;
        const __nv_bfloat16* pd = P.w_down + (size_t)b * 32768 + t2 * 64;
        PROF(2, t2 == 0, 13);
#pragma unroll 1
        for (int i = 0; i < WN; i += WB) {
          uint32_t v[WB];
#pragma unroll
          for (int u = 0; u < WB; u++)
            asm volatile("ld.global.cg.L2::128B.u32 %0, [%1];" : "=r"(v[u]) : "l"(i < 16 ? pg + (size_t)(i + u) * 64 * FF : pd + (i + u - 16) * 4096));
#pragma unroll
          for (int u = 1; u < WB; u++) v[0] ^= v[u];
          sts1(par + PAR_SINK + t2 * 4, v[0]);
        }
        PROF(2, t2 == 0, 14);
      }
      const uint32_t tag = epoch % 3 + 1;
      mbar_wait(bar_go, 0);
      if (warp == 10) {
        const uint32_t* src = g_mod + 2 * DM + cj * 128 + lane * 4;
        const uint2 wr = *reinterpret_cast<const uint2*>(P.w_r + cj * 128 + lane * 4);
        uint4 vga, vsb, vcb, vgb;
        uint32_t n = 0;
        do {
          vga = ld_relaxed4(src); vsb = ld_relaxed4(src + DM); vcb = ld_relaxed4(src + 2 * DM); vgb = ld_relaxed4(src + 3 * DM);
          watchdog(n);
        } while (!(tag_ok(vga, tag) && tag_ok(vsb, tag) && tag_ok(vcb, tag) && tag_ok(vgb, tag)));
        const float c0 = rbf(1.f + bf_hi(vcb.x)), c1 = rbf(1.f + bf_hi(vcb.y)), c2 = rbf(1.f + bf_hi(vcb.z)), c3 = rbf(1.f + bf_hi(vcb.w));
        const float a0 = c0 * bf_lo(wr.x), a1 = c1 * bf_hi(wr.x), a2 = c2 * bf_lo(wr.y), a3 = c3 * bf_hi(wr.y);
        const uint32_t h0 = pack_bf(a0, a1), h1 = pack_bf(a2, a3);
        const uint32_t t1 = par + PAR_T1 + (lane >> 2) * 64 + (lane & 1) * 32 + (lane & 2) * 2;
        sts1(t1, h0); sts1(t1 + 8, pack_bf(a0 - bf_lo(h0), a1 - bf_hi(h0)));
        sts1(t1 + 16, h1); sts1(t1 + 24, pack_bf(a2 - bf_lo(h1), a3 - bf_hi(h1)));
        sts4(par + PAR_T2 + lane * 32, make_uint4(pack_bf(c0, c1), __byte_perm(vsb.x, vsb.y, 0x7632), __byte_perm(vgb.x, vgb.y, 0x7632), __byte_perm(vga.x, vga.y, 0x7632)));
        sts4(par + PAR_T2 + lane * 32 + 16, make_uint4(pack_bf(c2, c3), __byte_perm(vsb.z, vsb.w, 0x7632), __byte_perm(vgb.z, vgb.w, 0x7632), __byte_perm(vga.z, vga.w, 0x7632)));
      } else if (lane < 4) {
        const uint4 g = poll4(lane < 2 ? g_mod + 5 * DM + b * 8 + lane * 4 : g_mod + 16 - lane * 4, tag);
        if (lane < 2) sts4(par + PAR_CONST + 16 + lane * 16, g);
        else sts2(par + PAR_CONST + (lane - 2) * 8, __float_as_uint(untag_sum(g.x, g.y) + untag_sum(g.z, g.w)), epoch);
      }
      __syncwarp();
#pragma unroll 4
      for (int q = XR; q < XE; q++) st_b128(g_xch + ((size_t)b * 8 * 256 + q * 64 + t2) * 4, (epoch & 1) << 16, 0, 0, 0);
      for (int q = 0; q < 2; q++) st_relaxed4(g_stats + ((size_t)cj * SEQ + rb * 128 + q * 64 + t2) * 4, 0, 0, 0, 0);
      if (b < NFFN)
        for (int q = 0; q < 4; q++) st_relaxed4(g_ypart + ((size_t)(q * 32 + (t2 >> 1)) * NFFN + b) * 8 + (t2 & 1) * 4, 0, 0, 0, 0);
      st_relaxed4(g_row + rb * 2 * DM + (t2 >> 5) * DM + cj * 128 + (t2 & 31) * 4, 0, 0, 0, 0);
      if (t2 < 16) st_relaxed2(g_cand + (cj * 16 + t2) * 32 + rb * 2, 0, 0);
      __threadfence();
      mbar_arrive(bar_par);
    }
    __syncwarp();
    cluster_arrive();
    {
      const uint32_t tag = epoch % 3 + 1, t3 = tid - 256;
      mbar_wait(bar_win, 0);
      const uint2 win = lds2(par + PAR_CONST + 56);
      const uint32_t* fsrc = g_row + (win.y >> 7) * 2 * DM + (b >> 1) * 16 + (t3 & 3) * 4 + (b & 1) * 2;
      const uint32_t* ysrc = g_ypart + ((size_t)b * NFFN + min(t3, NFFN - 1)) * 8;
      uint2 fh = ld_pair(fsrc), fx = ld_pair(fsrc + DM);
      uint4 ya = ld_relaxed4(ysrc), yb = ld_relaxed4(ysrc + 4);
      const float rwin = __uint_as_float(((int)win.x < 0 ? win.x & 0x7fffffffu : ~win.x) & ~3u);
      const float rs = rbf(rcp(1.f + __expf(-rbf(rwin))));
      uint32_t n = 0;
      while (fh.y != tag || fx.y != tag) { fh = ld_pair(fsrc); fx = ld_pair(fsrc + DM); watchdog(n); }
      while (!(tag_ok(ya, tag) && tag_ok(yb, tag))) { ya = ld_relaxed4(ysrc); yb = ld_relaxed4(ysrc + 4); watchdog(n); }
      __syncwarp();
      PROF(8, t3 == 0, 5);
      const uint32_t msk = t3 < NFFN ? ~3u : 0u;
      float y[8] = {__uint_as_float(ya.x & msk), __uint_as_float(ya.y & msk), __uint_as_float(ya.z & msk), __uint_as_float(ya.w & msk),
                    __uint_as_float(yb.x & msk), __uint_as_float(yb.y & msk), __uint_as_float(yb.z & msk), __uint_as_float(yb.w & msk)};
#pragma unroll
      for (int h = 4; h > 0; h >>= 1) {
        const bool up = lane & (h * 4);
#pragma unroll
        for (int e = 0; e < h; e++) y[e] = (up ? y[e + h] : y[e]) + __shfl_xor_sync(0xffffffffu, up ? y[e] : y[e + h], h * 4);
      }
      y[0] += __shfl_xor_sync(0xffffffffu, y[0], 1);
      y[0] += __shfl_xor_sync(0xffffffffu, y[0], 2);
      if ((lane & 3) == 0) sts1(par + PAR_RED + 64 + t3, __float_as_uint(y[0]));
      bar_sync(4, 128);
      if (t3 < 4) {
        float y0 = 0.f, y1 = 0.f;
#pragma unroll
        for (int w4 = 0; w4 < 4; w4++) {
          const uint2 v = lds2(par + PAR_RED + 64 + w4 * 32 + t3 * 8);
          y0 += __uint_as_float(v.x); y1 += __uint_as_float(v.y);
        }
        const uint2 gv = lds2(par + PAR_CONST + 16 + t3 * 8);
        const uint32_t upd = hmul2(pack_bf(y0, y1), pack_bf(rs, rs));
        *reinterpret_cast<uint32_t*>(P.out + (size_t)win.y * DM + b * 8 + t3 * 2) =
            hadd2(fx.x, hmul2(__byte_perm(gv.x, gv.y, 0x7632), hadd2(fh.x, upd)));
        if (b == 0 && t3 == 0) st_relaxed(&g_epoch, epoch + 1);
      }
      PROF(31, t3 == 0, 36);
    }
    cluster_wait();
  } else {
    const int wg = warp >> 2;

    uint32_t tag;
    {
      uint32_t* const pmod = g_modp + rank * 2 * DM + (b >> 1) * 32 + lane;
      uint32_t* const pln = g_ln1 + (rb * 128 + cj * 16 + warp) * 4;
      const uint32_t cv = ldg_nc1(P.c + rank * 512 + tid * 2);
      const uint32_t epoch = ld_relaxed(&g_epoch);
      if (warp == 0) st_relaxed(pmod, 0);
      if (lane == 0) { st_relaxed2(pln, 0, 0); st_relaxed2(pln + 32, 0, 0); }
      asm volatile("setmaxnreg.inc.sync.aligned.u32 232;");
      sts1(par + tid * 4, pack_bf(silu_f(bf_lo(cv)), silu_f(bf_hi(cv))));
      bar_sync(1, 320);
      tag = epoch % 3 + 1;
#pragma unroll
      for (int part = 0; part < 3; part++) {
        if (part != 1) {
          const uint32_t xa = base + (2 + part / 2) * GST_BYTES + warp * 2048 + lane * 16;
          mbar_wait(bar_hx + part * 4, 0);
          float s0 = 0.f, s1 = 0.f, q0 = 0.f, q1 = 0.f;
#pragma unroll
          for (int q = 0; q < 4; q++) {
            const uint4 xv = lds4(xa + q * 512);
            const uint32_t u[4] = {xv.x, xv.y, xv.z, xv.w};
#pragma unroll
            for (int e = 0; e < 4; e++) { const float lo = bf_lo(u[e]), hi = bf_hi(u[e]); s0 += lo; s1 += hi; q0 += lo * lo; q1 += hi * hi; }
          }
          s0 += s1; q0 += q1;
#pragma unroll
          for (int o = 16; o > 0; o >>= 1) { s0 += __shfl_xor_sync(0xffffffffu, s0, o); q0 += __shfl_xor_sync(0xffffffffu, q0, o); }
          const float mean = s0 * (1.f / DM);
          float mb, sd;
          ln_scalars(mean, fmaxf(q0 * (1.f / DM) - mean * mean, 0.f), mb, sd);
          if (lane == 0) st_relaxed2(pln + part * 16, __float_as_uint(mb) | tag, __float_as_uint(sd) | tag);
          PROF(1, tid == 0 && part == 2, 4);
        } else {
          float acc[8];
#pragma unroll
          for (int e = 0; e < 8; e++) acc[e] = 0.f;
          const uint32_t wa = stage + (tid >> 2) * 64 + (((tid ^ (tid >> 3)) & 3) << 4), sa = par + (tid >> 3) * 4, sh = (tid & 4) ? 0x3244 : 0x1044;
          mbar_wait(bar_hw, 0);
#pragma unroll
          for (int p = 0; p < 8; p++) {
            const uint4 w = lds4(wa + p * 4096);
            const float s = __uint_as_float(__byte_perm(lds1(sa + p * 128), 0, sh));
            acc[0] += s * bf_lo(w.x); acc[1] += s * bf_hi(w.x); acc[2] += s * bf_lo(w.y); acc[3] += s * bf_hi(w.y);
            acc[4] += s * bf_lo(w.z); acc[5] += s * bf_hi(w.z); acc[6] += s * bf_lo(w.w); acc[7] += s * bf_hi(w.w);
          }
#pragma unroll
          for (int e = 0; e < 4; e++) {
            const bool up = lane & 16;
            acc[e] = (up ? acc[e + 4] : acc[e]) + __shfl_xor_sync(0xffffffffu, up ? acc[e] : acc[e + 4], 16);
          }
#pragma unroll
          for (int e = 0; e < 2; e++) {
            const bool up = lane & 8;
            acc[e] = (up ? acc[e + 2] : acc[e]) + __shfl_xor_sync(0xffffffffu, up ? acc[e] : acc[e + 2], 8);
          }
          {
            const bool up = lane & 4;
            acc[0] = (up ? acc[1] : acc[0]) + __shfl_xor_sync(0xffffffffu, up ? acc[0] : acc[1], 4);
          }
          sts1(par + 1024 + warp * 128 + ((lane & 3) * 8 + (lane >> 2)) * 4, __float_as_uint(acc[0]));
          bar_sync(1, 256);
          if (warp == 0) {
            float s = 0.f;
#pragma unroll
            for (int w8 = 0; w8 < 8; w8++) s += __uint_as_float(lds1(par + 1024 + w8 * 128 + lane * 4));
            st_relaxed(pmod, (__float_as_uint(s) & ~3u) | tag);
          }
          PROF(1, tid == 0, 3);
        }
      }
      {
        uint2 s0 = ld_relaxed2(g_ln1 + (rb * 128 + (tid & 127)) * 4);
        uint4 v[4];
#pragma unroll
        for (int q = 0; q < 4; q++) v[q] = ld_relaxed4(g_modp + q * DM + tid * 4);
        {
          uint32_t n = 0;
          while (!(tag_ok(v[0], tag) && tag_ok(v[1], tag) && tag_ok(v[2], tag) && tag_ok(v[3], tag))) {
#pragma unroll
            for (int q = 0; q < 4; q++)
              if (!tag_ok(v[q], tag)) v[q] = ld_relaxed4(g_modp + q * DM + tid * 4);
            if (((s0.x ^ tag) | (s0.y ^ tag)) & 3u) s0 = ld_relaxed2(g_ln1 + (rb * 128 + (tid & 127)) * 4);
            watchdog(n);
          }
        }
        const uint32_t d = stage + (tid >> 2) * 64 + (tid & 1) * 32 + (tid & 2) * 2;
        sts1(d, pack_bf(1.f + rbf(untag_sum(v[1].x, v[3].x)), 1.f + rbf(untag_sum(v[1].y, v[3].y))));
        sts1(d + 16, pack_bf(1.f + rbf(untag_sum(v[1].z, v[3].z)), 1.f + rbf(untag_sum(v[1].w, v[3].w))));
        sts1(d + 8, pack_bf(untag_sum(v[0].x, v[2].x), untag_sum(v[0].y, v[2].y)));
        sts1(d + 24, pack_bf(untag_sum(v[0].z, v[2].z), untag_sum(v[0].w, v[2].w)));
        if (wg == 0) {
          uint32_t n = 0;
          while (((s0.x ^ tag) | (s0.y ^ tag)) & 3u) { s0 = ld_relaxed2(g_ln1 + (rb * 128 + tid) * 4); watchdog(n); }
          uint32_t ih, il;
          split_inv(bf_hi(s0.y), ih, il);
          sts4(stage + 4096 + tid * 16, make_uint4(__byte_perm(s0.x, 0, 0x3232), ih, il, 0));
        }
        mbar_arrive(bar_mod);
      }
      cluster_wait();
      if (wg == 1) bar_arrive(2, 256);
      mbar_wait(bar_mod, 0);
      PROF(1, tid == 0, 2);
    }

    float f0 = 0.f, f1 = 0.f;
    const uint32_t rempty = lane < 2 ? mapa(bempty, lane & 1) : 0;
    constexpr uint32_t GE = NSLOT * 8 + 32;
    float o[64], s[64];
#pragma unroll 1
    for (int ps = 0; ps < 3; ps++) {
      {
        const uint32_t xt = ps == 1 ? XT1 : XT2, wt = ps == 1 ? WT1 : WT2;
        const int nst = ps == 2 ? 28 : 14;
        if (ps == 0) {
          float ga[64], gb[64];
#pragma unroll
          for (int i = 0; i < 64; i++) { ga[i] = 0.f; gb[i] = 0.f; }
          uint32_t a[2][16];
          const uint32_t l = fresh_lane();
          const uint4 r0 = lds4(stage + 4096 + (warp * 16 + (l >> 2)) * 16), r1 = lds4(stage + 4096 + 128 + (warp * 16 + (l >> 2)) * 16);
          auto transform = [&](int i, uint32_t (&f)[16], uint32_t z) {
            const uint32_t ad = base + (i & 3) * GST_BYTES + wg * 8192 + frag_offset(warp) + z;
            mbar_wait(xfull + (i & 3) * 8, i >> 2);
#pragma unroll
            for (int kk = 0; kk < 4; kk++) ldmatrix4(ad ^ (kk * 32), f[4 * kk], f[4 * kk + 1], f[4 * kk + 2], f[4 * kk + 3]);
#pragma unroll
            for (int kk = 0; kk < 4; kk++) {
              const uint4 m = lds4(stage + (l & 3) * 16 + ((2 * cj + i) & 15) * 256 + kk * 64);
              f[4 * kk] = ln_mod(f[4 * kk], r0.x, r0.y, r0.z, m.x, m.z);
              f[4 * kk + 1] = ln_mod(f[4 * kk + 1], r1.x, r1.y, r1.z, m.x, m.z);
              f[4 * kk + 2] = ln_mod(f[4 * kk + 2], r0.x, r0.y, r0.z, m.y, m.w);
              f[4 * kk + 3] = ln_mod(f[4 * kk + 3], r1.x, r1.y, r1.z, m.y, m.w);
            }
            keep(f);
            mbar_arrive_pred(xempty + (i & 3) * 8, l == 0);
          };
          auto publish = [&](int u, uint32_t (&f)[16]) {
            const uint32_t sc = stage + 8192 + wg * 8192;
#pragma unroll
            for (int kk = 0; kk < 4; kk++) stmatrix4((sc + frag_offset(warp)) ^ (kk * 32), f[4 * kk], f[4 * kk + 1], f[4 * kk + 2], f[4 * kk + 3]);
            __syncwarp();
            const uint32_t src = sc + (warp & 3) * 2048 + l * 16;
            uint8_t* dst = g_act + (uint32_t)(rb * 80 + cj * 2 + u) * UNIT + warp * 2048 + l * 16;
#pragma unroll
            for (int p4 = 0; p4 < 4; p4++) stg4(dst + p4 * 512, lds4(src + p4 * 512));
            __syncwarp();
            if (u == 1) mbar_arrive_pred(bar_hpub, l == 0);
          };
          auto multiply = [&](int i, uint32_t (&f)[16]) {
            mbar_wait(gfull + (i & 3) * 8, i >> 2);
            const uint64_t db = make_desc(base + (i & 3) * GST_BYTES + UNIT, 8192, 1024);
            wg_fence();
#pragma unroll
            for (int kk = 0; kk < 4; kk++) mma256_rs(ga, gb, f[4 * kk], f[4 * kk + 1], f[4 * kk + 2], f[4 * kk + 3], db + kk * 128);
            wg_commit();
          };
          transform(0, a[0], 0); publish(0, a[0]); transform(1, a[1], 0); multiply(0, a[0]); publish(1, a[1]);
#pragma unroll
          for (int i = 1; i < NRS; i++) {
            if (i >= 2) {
              uint32_t z = r0.w;
#pragma unroll
              for (int k = 0; k < 16; k += 2) asm volatile("lop3.b32 %0, %1, %2, %0, 0xA8;" : "+r"(z) : "r"(a[i & 1][k]), "r"(a[i & 1][k + 1]));
              transform(i, a[i & 1], z);
            }
            multiply(i, a[i & 1]);
            wg_wait<1>();
            mbar_arrive_cl(rempty, GE + ((i + 3) & 3) * 8);
          }
          mbar_arrive_pred(bar_pread, l == 0);
#pragma unroll 1
          for (int i = NRS; i < 14; i++) {
            mbar_wait(xfull + (i & 3) * 8, (i >> 2) & 1);
            mbar_wait(gfull + (i & 3) * 8, (i >> 2) & 1);
            const uint32_t xa = base + (i & 3) * GST_BYTES;
            const uint64_t da = make_desc(xa + wg * 8192, 16, 1024), db = make_desc(xa + UNIT, 8192, 1024);
            if (i == 13) bar_sync(2 + wg, 256);
            wg_fence();
#pragma unroll
            for (int kk = 0; kk < 4; kk++) mma256_ss(ga, gb, da + kk * 2, db + kk * 128, 1);
            wg_commit();
            if (i == 13) bar_arrive(3 - wg, 256);
            wg_wait<1>();
            uint32_t z = r0.w;
#pragma unroll
            for (int k = 0; k < 16; k += 2) asm volatile("lop3.b32 %0, %1, %2, %0, 0xA8;" : "+r"(z) : "r"(a[1][k]), "r"(a[1][k + 1]));
            mbar_arrive_cl(rempty, GE + ((i + 3) & 3) * 8 + z);
            mbar_arrive_pred(xempty + ((i + 3) & 3) * 8, l == 0 && i != NRS);
          }
          mbar_wait(xfull + 16, 1);
          mbar_wait(xfull + 24, 1);
          wg_wait<0>();
          keep(ga); keep(gb);
#pragma unroll
          for (int i = 0; i < 64; i++) {
            asm volatile("mov.b32 %0, %1;" : "=f"(s[i]) : "f"(ga[i]));
            asm volatile("mov.b32 %0, %1;" : "=f"(o[i]) : "f"(gb[i]));
          }
        } else {
          float ga[64], gb[64];
#pragma unroll
          for (int i = 0; i < 64; i++) {
            asm volatile("mov.b32 %0, %1;" : "=f"(ga[i]) : "f"(s[i]));
            asm volatile("mov.b32 %0, %1;" : "=f"(gb[i]) : "f"(o[i]));
          }
#pragma unroll 1
          for (int i = 0; i < nst; i++) {
            mbar_wait(gfull + (i & 3) * 8, (i >> 2) & 1);
            const uint64_t da = make_desc(base + unit_of(xt, i & 3) + wg * 8192, 16, 1024), db = make_desc(base + unit_of(wt, i & 3), 8192, 1024);
            if (i == nst - 1) bar_sync(2 + wg, 256);
            wg_fence();
#pragma unroll
            for (int kk = 0; kk < 4; kk++) mma256_ss(ga, gb, da + kk * 2, db + kk * 128, kk ? 1 : i);
            wg_commit();
            if (i == nst - 1) bar_arrive(3 - wg, 256);
            wg_wait<1>();
            mbar_arrive_cl(rempty, GE + ((i + 3) & 3) * 8, i != 0);
            PROF(4, tid == 0 && (i & 3) == 0, 40 + (ps - 1) * 4 + i / 4);
          }
          wg_wait<0>();
          keep(ga); keep(gb);
#pragma unroll
          for (int i = 0; i < 64; i++) {
            asm volatile("mov.b32 %0, %1;" : "=f"(s[i]) : "f"(ga[i]));
            asm volatile("mov.b32 %0, %1;" : "=f"(o[i]) : "f"(gb[i]));
          }
        }
        mbar_arrive_cl(rempty, GE + (ps == 2 ? 24 : 8));
        if (ps == 2) break;
      }
      const uint32_t qw = base + wg * 8192, qt = QT >> (16 * ps), at = ps ? AT1 : AT0;
      {
        const uint32_t wt = ps ? WT1 : WT0;
        const uint64_t da0 = make_desc(qw + unit_of(qt, 2), 16, 1024), da1 = make_desc(qw + unit_of(qt, 3), 16, 1024);
        const uint64_t db0 = make_desc(base + unit_of(wt, 2), 8192, 1024), db1 = make_desc(base + unit_of(wt, 3), 8192, 1024);
        mbar_wait(gfull + 16, 1);
        mbar_wait(gfull + 24, 1);
        bar_sync(2 + wg, 256);
        wg_fence();
#pragma unroll
        for (int kk = 0; kk < 8; kk++) mma_ss<1>(s, (kk < 4 ? da0 : da1) + (kk & 3) * 2, (kk < 4 ? db0 : db1) + (kk & 3) * 128, 1);
        wg_commit();
        bar_arrive(3 - wg, 256);
        mbar_wait(ps == 0 ? bar_pread : bar_ofree + 8, 0);
        mbar_wait(bfull, 0);
        wg_wait<0>();
        keep(s);
        PROF(2, tid == 0, 8 + ps * 8);
        store_chunk<0>(s, qw + unit_of(qt, 0) + frag_offset(warp));
        store_chunk<1>(s, qw + unit_of(qt, 1) + frag_offset(warp));
        fence_async_smem();
        bar_sync(2 + wg, 256);
        wg_fence();
        issue_qk(s, qw + unit_of(qt, 0), qw + unit_of(qt, 1), base + unit_of(at, 0));
        wg_commit();
#pragma unroll
        for (int kk = 0; kk < 8; kk++) mma_ss<1>(o, (kk < 4 ? da0 : da1) + (kk & 3) * 2, (kk < 4 ? db0 : db1) + UNIT / 16 + (kk & 3) * 128, 1);
        wg_commit();
        bar_arrive(3 - wg, 256);
        wg_wait<1>();
        keep(s);
        mbar_arrive_cl(rempty, 0);
      }
      PROF(4, tid == 0 && ps == 1, 61);
      float l0 = 0.25f, l1 = 0.25f;
      auto step = [&](auto odd_c, const int j, uint32_t (&pw)[32], uint32_t (&pr)[32]) {
        constexpr bool ODD = decltype(odd_c)::value;
        const bool first = !ODD && (j & 2) == 0, last = ODD && j == 7;
        const uint32_t ph = (j >> 1) & 1;
        float i0, i1, a0, a1;
        if (first) { i0 = inv_quad_sum(l0); i1 = inv_quad_sum(l1); l0 = 0.f; l1 = 0.f; }
        bool redo = !ODD && (j | ps) == 0, again = false;
        while (true) {
          if (redo) {
            float m0 = fmaxf(s[0], s[1]), m1 = fmaxf(s[2], s[3]);
#pragma unroll
            for (int i = 1; i < 16; i++) { m0 = fmaxf(m0, fmaxf(s[4 * i], s[4 * i + 1])); m1 = fmaxf(m1, fmaxf(s[4 * i + 2], s[4 * i + 3])); }
            m0 = fmaxf(m0, __shfl_xor_sync(0xffffffffu, m0, 1)); m1 = fmaxf(m1, __shfl_xor_sync(0xffffffffu, m1, 1));
            m0 = fmaxf(m0, __shfl_xor_sync(0xffffffffu, m0, 2)); m1 = fmaxf(m1, __shfl_xor_sync(0xffffffffu, m1, 2));
            m0 *= SCL2; m1 *= SCL2;
            if (!first) {
              m0 = fmaxf(m0, f0); m1 = fmaxf(m1, f1);
              const float c0 = ex2(f0 - m0), c1 = ex2(f1 - m1);
              l0 *= c0; l1 *= c1;
              wg_wait<0>();
              keep(o);
#pragma unroll
              for (int i = 0; i < 16; i++) { o[4 * i] *= c0; o[4 * i + 1] *= c0; o[4 * i + 2] *= c1; o[4 * i + 3] *= c1; }
            }
            f0 = m0; f1 = m1;
          }
          float b0 = 0.f, b1 = 0.f;
          a0 = 0.f; a1 = 0.f;
#pragma unroll
          for (int i = 0; i < 16; i++) {
            const float e0 = ex2(fmaf(s[4 * i], SCL2, -f0)), e1 = ex2(fmaf(s[4 * i + 1], SCL2, -f0));
            const float e2 = ex2(fmaf(s[4 * i + 2], SCL2, -f1)), e3 = ex2(fmaf(s[4 * i + 3], SCL2, -f1));
            a0 += e0; b0 += e1; a1 += e2; b1 += e3;
            pw[2 * i] = pack_bf(e0, e1); pw[2 * i + 1] = pack_bf(e2, e3);
            if (i == VREL) {
#pragma unroll
              for (int k = 0; k < 2 * VREL + 2; k++) asm volatile("" : "+r"(pw[k])::"memory");
              mbar_wait(bfull + (ODD ? 24 : 8), ph);
              wg_wait<0>();
              mbar_arrive_cl(rempty, ODD ? 16 : (j ? 0 : GE + 16), !again);
              if (!ODD) mbar_arrive_cl(rempty, GE + 24, !again && j == 0);
#pragma unroll
              for (int k = 4 * VREL + 4; k < 64; k++) asm volatile("" : "+f"(s[k])::"memory");
            }
          }
          a0 += b0; a1 += b1;
          if (redo) break;
          redo = __any_sync(0xffffffffu, !(a0 + a1 < 0x1p70f));
          if (first) {
            uint32_t m0 = __ballot_sync(0xffffffffu, a0 > 0x1p-50f), m1 = __ballot_sync(0xffffffffu, a1 > 0x1p-50f);
            m0 |= m0 >> 1; m1 |= m1 >> 1; m0 |= m0 >> 2; m1 |= m1 >> 2;
            redo = redo || (m0 & m1 & 0x11111111u) != 0x11111111u;
          }
          if (!redo) break;
          again = true;
        }
        l0 += a0; l1 += a1;
        keep(pw);
        keep(o);
        const uint32_t qo = qt >> (j ? 0 : 8);
        if (first) store_chunk<0>(o, i0, i1, qw + unit_of(qo, 0) + frag_offset(warp));
        keep(o);
        bar_sync(2 + wg, 256);
        if (!last) {
          const uint32_t qn = qt >> (j >= 3 ? 8 : 0);
          wg_fence();
          issue_qk(s, qw + unit_of(qn, 0), qw + unit_of(qn, 1), base + unit_of(at, ODD ? 3 : 1));
          wg_commit();
          mbar_wait(bfull + (ODD ? 0 : 16), ODD ? ph ^ 1 : ph);
        }
        if (first) { store_chunk<1>(o, i0, i1, qw + unit_of(qo, 1) + frag_offset(warp)); keep(o); }
        wg_fence();
        issue_pv(o, pw, base + unit_of(at, ODD ? (last ? 3 : 0) : 2), !first);
        wg_commit();
        bar_arrive(3 - wg, 256);
        if (first) { fence_async_smem(); mbar_arrive_pred(bar_ofull + wg * 8, j); PROF(2, tid == 0 && j, 9 + ps * 8); }
        wg_wait<1>();
        keep(s);
        mbar_arrive_cl(rempty, ODD ? 24 : 8, !last);
        PROF(4, tid == 0 && ps == 1, 51 + j);
      };
      uint32_t pa[32], pb[32];
#pragma unroll 1
      for (int j = 0; j < 8; j += 2) {
        step(std::false_type{}, j, pa, pb);
        step(std::true_type{}, j + 1, pb, pa);
      }
      {
        const float i0 = inv_quad_sum(l0), i1 = inv_quad_sum(l1);
        wg_wait<0>();
        keep(o);
        mbar_arrive_cl(rempty, 24);
        store_chunk<0>(o, i0, i1, qw + unit_of(qt, 2) + frag_offset(warp));
        store_chunk<1>(o, i0, i1, qw + unit_of(qt, 3) + frag_offset(warp));
        fence_async_smem();
        mbar_arrive(bar_ofull + wg * 8);
      }
      PROF(2, tid == 0, 10 + ps * 8);
    }

    const int ln = fresh_lane(), g = ln >> 2, tq = ln & 3, ct = warp * 32 + ln;
    const bool lane0 = ln == 0;
    const int lrow0 = warp * 16 + g;
    const int grow0 = rb * 128 + lrow0;
    const uint32_t res = base + OFF_RES, trow = res + wg * 8192 + frag_offset(warp);
    uint32_t xr[32];
    {
      const uint64_t da = make_desc(base + wg * 8192, 16, 1024), db = make_desc(base, 8192, 1024);
      constexpr int U = UNIT / 16;
#define HALF_STAGE(acc, xu, wu) _Pragma("unroll") for (int kk = 0; kk < 4; kk++) mma_ss<1>(acc, da + (xu) * U + kk * 2, db + (wu) * U + kk * 128, 1)
      PROF(10, ct == PT, 19); STAMP(0);
      cluster_arrive();
      mbar_wait(gfull, 1);
      mbar_wait(gfull + 8, 1);
      bar_sync(2 + wg, 256);
      wg_fence();
      HALF_STAGE(o, 6, 8);
      HALF_STAGE(o, 9, 11);
      wg_commit();
      STAMP(16);
      mbar_wait(gfull + 16, 1);
      STAMP(17);
      wg_fence();
      HALF_STAGE(o, 12, 1);
      wg_commit();
      bar_arrive(3 - wg, 256);
      mbar_wait(bar_par, 0);
      uint32_t* xo = g_xch + ((size_t)b * 8 * 256 + ct) * 4;
      const uint32_t* xi = g_xch + ((size_t)(b ^ 2) * 8 * 256 + ct) * 4;
      const uint32_t par1 = (~lds1(par + PAR_CONST + 4) & 1) << 16;
      wg_wait<0>();
      keep(o);
      mbar_arrive_pred(bar_ring, lane0);
      PROF(8, ct == PT, 20); STAMP(1);
#define SEND(i) st_b128(xo + (i) * 1024, (pack_bf(o[8 * (i)], o[8 * (i) + 1]) & ~0x10000u) | par1, pack_bf(o[8 * (i) + 2], o[8 * (i) + 3]), \
                        pack_bf(o[8 * (i) + 4], o[8 * (i) + 5]), pack_bf(o[8 * (i) + 6], o[8 * (i) + 7]))
#pragma unroll
      for (int i = 0; i < NS1; i++) SEND(i);
      PROF(8, ct == PT, 21); STAMP(2);
      bar_sync(2 + wg, 256);
      wg_fence();
      HALF_STAGE(s, 6, 7);
      HALF_STAGE(s, 9, 10);
      HALF_STAGE(s, 12, 0);
      wg_commit();
      bar_arrive(3 - wg, 256);
      STAMP(18);
      mbar_wait(gfull + 24, 1);
#pragma unroll
      for (int i = NS1; i < 8; i++) SEND(i);
      uint4 v[8];
#pragma unroll
      for (int i = 0; i < 4; i++) v[i] = ld_b128(xi + i * 1024);
      STAMP(19);
      mbar_wait(bar_rx, 0);
      wg_wait<0>();
      mbar_arrive_pred(bar_ring + 8, lane0);
      bar_sync(2 + wg, 256);
      STAMP(20);
#pragma unroll
      for (int i = 4; i < 8; i++) v[i] = ld_b128(xi + i * 1024);
      mbar_wait(bar_xres, 0);
      wg_fence();
      HALF_STAGE(s, 13, 2);
      HALF_STAGE(s, 8, 3);
      wg_commit();
      bar_arrive(3 - wg, 256);
      STAMP(21);
      wg_wait<0>();
      keep(s);
      mbar_arrive_pred(bar_ring + 16, lane0);
      PROF(10, ct == PT, 23); STAMP(4);
#pragma unroll
      for (int i = 0; i < 16; i += 2) ldmatrix4((trow ^ ((i & 7) << 4)) + (i >> 3) * 16384, xr[2 * i], xr[2 * i + 1], xr[2 * i + 2], xr[2 * i + 3]);
      {
        uint32_t n = 0;
        bool ok;
        do {
          ok = true;
#pragma unroll
          for (int i = 0; i < 8; i++)
            if ((v[i].x & 0x10000u) != par1) { v[i] = ld_b128(xi + i * 1024); ok = false; }
          watchdog(n);
        } while (!ok);
      }
      __syncwarp();
      PROF(8, ct == PT, 22); STAMP(3);
      float ds[4] = {0.f, 0.f, 0.f, 0.f}, dl[4] = {0.f, 0.f, 0.f, 0.f}, q0[4] = {0.f, 0.f, 0.f, 0.f}, q1[4] = {0.f, 0.f, 0.f, 0.f};
#pragma unroll
      for (int i = 0; i < 8; i++) {
        const uint32_t ga0 = lds1(par + PAR_T2 + i * 128 + tq * 16 + 12), ga1 = lds1(par + PAR_T2 + i * 128 + 64 + tq * 16 + 12);
        const uint4 bw = lds4(par + PAR_T1 + i * 64 + tq * 16);
        const uint32_t u0 = hfma2(ga0, hadd2(pack_bf(s[8 * i], s[8 * i + 1]), v[i].x & ~0x10000u), xr[4 * i]);
        const uint32_t u1 = hfma2(ga0, hadd2(pack_bf(s[8 * i + 2], s[8 * i + 3]), v[i].y), xr[4 * i + 1]);
        const uint32_t u2 = hfma2(ga1, hadd2(pack_bf(s[8 * i + 4], s[8 * i + 5]), v[i].z), xr[4 * i + 2]);
        const uint32_t u3 = hfma2(ga1, hadd2(pack_bf(s[8 * i + 6], s[8 * i + 7]), v[i].w), xr[4 * i + 3]);
        xr[4 * i] = u0; xr[4 * i + 1] = u1; xr[4 * i + 2] = u2; xr[4 * i + 3] = u3;
        mma16816(ds, u0, u1, u2, u3, (g & 1) ? bw.x : 0x3f803f80u, (g & 1) ? bw.y : 0x3f803f80u);
        mma16816(dl, u0, u1, u2, u3, bw.z, bw.w);
        mma16816(q0, u0, u1, u2, u3, u0, u2);
        mma16816(q1, u0, u1, u2, u3, u1, u3);
      }
      if (tq == (g >> 1)) {
        uint32_t* dst = g_stats + ((size_t)cj * SEQ + grow0) * 4;
        st_b128(dst, __float_as_uint(ds[0]), __float_as_uint((g & 1) ? q0[1] : q0[0]), __float_as_uint(ds[1] + dl[1]), tag);
        st_b128(dst + 32, __float_as_uint(ds[2]), __float_as_uint((g & 1) ? q1[3] : q1[2]), __float_as_uint(ds[3] + dl[3]), tag);
      }
    }
    PROF(8, ct == PT, 29); STAMP(5);
    uint32_t mm, ih, il;
    float rbest;
    {
      const uint32_t* sp = g_stats + ((size_t)(tq >> 1) * 4 * SEQ + grow0 + (tq & 1) * 8) * 4;
      uint4 v0 = ld_b128(sp), v1 = ld_b128(sp + SEQ * 4), v2 = ld_b128(sp + SEQ * 8), v3 = ld_b128(sp + SEQ * 12);
#pragma unroll
      for (int i = 0; i < 16; i += 2) stmatrix4((trow ^ ((i & 7) << 4)) + (i >> 3) * 16384, xr[2 * i], xr[2 * i + 1], xr[2 * i + 2], xr[2 * i + 3]);
      const uint4 cst = lds4(par + PAR_CONST);
      const float A1 = __uint_as_float(cst.x), A2 = __uint_as_float(cst.z);
      uint32_t n = 0;
      while (v0.w != tag || v1.w != tag || v2.w != tag || v3.w != tag) {
        if (v0.w != tag) v0 = ld_b128(sp);
        if (v1.w != tag) v1 = ld_b128(sp + SEQ * 4);
        if (v2.w != tag) v2 = ld_b128(sp + SEQ * 8);
        if (v3.w != tag) v3 = ld_b128(sp + SEQ * 12);
        watchdog(n);
      }
      __syncwarp();
      PROF(8, ct == PT, 30); STAMP(6);
      float su = (__uint_as_float(v0.x) + __uint_as_float(v1.x)) + (__uint_as_float(v2.x) + __uint_as_float(v3.x));
      float sq = (__uint_as_float(v0.y) + __uint_as_float(v1.y)) + (__uint_as_float(v2.y) + __uint_as_float(v3.y));
      float dt = (__uint_as_float(v0.z) + __uint_as_float(v1.z)) + (__uint_as_float(v2.z) + __uint_as_float(v3.z));
      su += __shfl_xor_sync(0xffffffffu, su, 2); sq += __shfl_xor_sync(0xffffffffu, sq, 2); dt += __shfl_xor_sync(0xffffffffu, dt, 2);
      const float m = su * (1.f / DM);
      float mb, sd;
      ln_scalars(m, fmaxf(sq * (1.f / DM) - m * m, 0.f), mb, sd);
      const float inv = rcp(sd);
      rbest = (dt - mb * A1) * inv + A2;
      mm = pack_bf(mb, mb);
      ih = pack_bf(inv, inv);
      const float lo = inv - bf_lo(ih);
      il = pack_bf(lo, lo);
    }
    int ibest;
    {
      const uint32_t bits = __float_as_uint(rbest) & ~3u, key = (int)bits < 0 ? ~bits : bits | 0x80000000u;
      const uint32_t kmax = __reduce_max_sync(0xffffffffu, key);
      const uint32_t row = __reduce_min_sync(0xffffffffu, key == kmax ? lrow0 + (tq & 1) * 8 : 255);
      if (lane0) sts2(par + PAR_RED + warp * 8, kmax, row);
      PROF(8, ct == PT, 38); STAMP(7);
      bar_sync(1, 256);
      const uint2 cv = lds2(par + PAR_RED + (ln & 7) * 8);
      const uint32_t k2 = __reduce_max_sync(0xffffffffu, cv.x);
      ibest = __reduce_min_sync(0xffffffffu, cv.x == k2 ? cv.y : 255);
      if (ct < 16) st_relaxed2(g_cand + (cj * 16 + ct) * 32 + rb * 2, (k2 & ~3u) | tag, ((rb * 128 + ibest) << 2) | tag);
    }
    PROF(8, ct == PT, 39); STAMP(8);
    if ((ibest >> 4) == warp) {
      const int src = (ibest & 7) * 4 + ((ibest >> 3) & 1), ch = g * 2;
      const uint32_t cm = __shfl_sync(0xffffffffu, mm, src), ch_ = __shfl_sync(0xffffffffu, ih, src), cl = __shfl_sync(0xffffffffu, il, src);
      const uint32_t xa = res + (ch >> 3) * 16384 + ibest * 128 + (((ch & 7) ^ (ibest & 7)) << 4) + tq * 4;
      const uint32_t x0 = lds1(xa), x1 = lds1(xa ^ 16);
      const uint2 p0 = lds2(par + PAR_T2 + ch * 64 + tq * 16), p1 = lds2(par + PAR_T2 + ch * 64 + 64 + tq * 16);
      uint32_t* dst = g_row + rb * 2 * DM + cj * 128 + ln * 4;
      st_pairs(dst, ln_mod(x0, cm, ch_, cl, p0.x, p0.y), ln_mod(x1, cm, ch_, cl, p1.x, p1.y), tag);
      st_pairs(dst + DM, x0, x1, tag);
      __syncwarp();
    }
    PROF(8, ct == PT, 37); STAMP(9);
    const uint32_t* inbox = g_cand + b * 32 + (ln & 15) * 2;
    uint2 cv = ld_relaxed2(inbox);
    uint32_t wf[128];
    const uint32_t frow = (ln & 7) + (ln >> 4) * 8;
    const uint32_t wfo = base + (warp & 1) * 8192 + frow * 64 + ((((ln >> 3) & 1) ^ ((frow >> 1) & 3)) << 4);
    if (b < NFFN) {
#pragma unroll
      for (int m = 0; m < 2; m++) {
        const uint32_t wfa = wfo + unit_of(m ? FT_U : FT_G, warp >> 1);
        mbar_wait(bar_box + (m * 4 + (warp >> 1)) * 8, 0);
#pragma unroll
        for (int f = 0; f < 16; f++) {
          const int r = ((f >> 1) * 4 + m * 2 + (f & 1)) * 4;
          ldmatrix4t((wfa ^ ((f & 1) * 32)) + (f >> 1) * 1024, wf[r], wf[r + 1], wf[r + 2], wf[r + 3]);
        }
      }
    }
    PROF(8, ct == PT, 31); STAMP(10);
    uint32_t kwin; int iwin;
    uint4 hv[8];
    uint32_t wd[64];
    const uint32_t wda = base + unit_of(FT_D, warp >> 1) + (warp & 1) * 8192 + frow * 128 + ((((ln >> 3) & 1) ^ (ln & 7)) << 4);
#define LOAD_WD(f) ldmatrix4t((wda ^ ((((f) >> 1) & 3) * 32)) + ((f) >> 3) * 4096 + ((f) & 1) * 2048, wd[4 * (f)], wd[4 * (f) + 1], wd[4 * (f) + 2], wd[4 * (f) + 3])
    {
      uint32_t n = 0;
      int cur = -1;
      while (true) {
        const bool valid = !(((cv.x ^ tag) | (cv.y ^ tag)) & 3u);
        const uint32_t key = valid ? cv.x : 0u;
        kwin = __reduce_max_sync(0xffffffffu, key);
        const int src = (__ffs(__ballot_sync(0xffffffffu, key == kwin)) - 1) & 15;
        if (kwin && src != cur) {
          cur = src;
#pragma unroll
          for (int i = 0; i < 8; i++) hv[i] = ld_pairs(g_row + cur * 2 * DM + warp * 128 + i * 16 + tq * 4);
        }
        if (__all_sync(0xffffffffu, valid)) break;
        cv = ld_relaxed2(inbox);
        watchdog(n);
      }
      iwin = __shfl_sync(0xffffffffu, cv.y, cur) >> 2;
    }
    PROF(8, ct == PT, 32); STAMP(11);
    const uint32_t* wrow = g_row + (iwin >> 7) * 2 * DM;
    if (b < NFFN) {
      {
        uint32_t n = 0;
        bool ok;
        do {
          ok = true;
#pragma unroll
          for (int i = 0; i < 8; i++)
            if (hv[i].y != tag || hv[i].w != tag) { hv[i] = ld_pairs(wrow + warp * 128 + i * 16 + tq * 4); ok = false; }
          watchdog(n);
        } while (!ok);
      }
      __syncwarp();
      PROF(8, ct == PT, 33); STAMP(12);
      float d[8][4];
#pragma unroll
      for (int i = 0; i < 8; i++) { d[i][0] = 0.f; d[i][1] = 0.f; d[i][2] = 0.f; d[i][3] = 0.f; }
#pragma unroll
      for (int ks = 0; ks < 8; ks++) {
#pragma unroll
        for (int mt = 0; mt < 4; mt++) {
          const int r = ks * 16 + mt * 4;
          mma16816(d[mt + (ks & 1) * 4], wf[r], wf[r + 1], wf[r + 2], wf[r + 3], hv[ks].x, hv[ks].z);
        }
        if (ks == 1) mbar_wait(bar_box + (8 + (warp >> 1)) * 8, 0);
        if (ks >= 1) {
#pragma unroll
          for (int f = 4 * ks - 4; f < 16 && f < 4 * ks; f++) LOAD_WD(f);
        }
      }
      if (tq == 0) {
        const uint32_t dst = base + unit_of(FT_G, warp >> 1) + (warp & 1) * 8192 + g * 32;
        sts4(dst, make_uint4(__float_as_uint(d[0][0] + d[4][0]), __float_as_uint(d[0][2] + d[4][2]), __float_as_uint(d[1][0] + d[5][0]), __float_as_uint(d[1][2] + d[5][2])));
        sts4(dst + 16, make_uint4(__float_as_uint(d[2][0] + d[6][0]), __float_as_uint(d[2][2] + d[6][2]), __float_as_uint(d[3][0] + d[7][0]), __float_as_uint(d[3][2] + d[7][2])));
      }
      bar_sync(1, 256);
      uint32_t ab[4];
      {
        float G = 0.f, U = 0.f;
        const uint32_t src = base + (ln & 7) * 32 + (ln >> 3) * 4;
#pragma unroll
        for (int w8 = 0; w8 < 8; w8++) {
          const uint32_t a = src + ((FT_G >> (w8 >> 1) * 4) & 15) * UNIT + (w8 & 1) * 8192;
          G += __uint_as_float(lds1(a)); U += __uint_as_float(lds1(a + 16));
        }
        const float act = rbf(silu_f(rbf(G))) * rbf(U);
        const uint32_t pk = pack_bf(act, __shfl_down_sync(0xffffffffu, act, 1));
#pragma unroll
        for (int i = 0; i < 4; i++) ab[i] = __shfl_sync(0xffffffffu, pk, i * 8 + tq * 2);
      }
      PROF(8, ct == PT, 34); STAMP(13);
#pragma unroll
      for (int mt = 0; mt < 8; mt++) {
        d[mt][0] = 0.f; d[mt][1] = 0.f; d[mt][2] = 0.f; d[mt][3] = 0.f;
        mma16816(d[mt], wd[mt * 8], wd[mt * 8 + 1], wd[mt * 8 + 2], wd[mt * 8 + 3], ab[0], ab[1]);
        mma16816(d[mt], wd[mt * 8 + 4], wd[mt * 8 + 5], wd[mt * 8 + 6], wd[mt * 8 + 7], ab[2], ab[3]);
      }
#pragma unroll
      for (int i = 0; i < 4; i++) {
        const int m4 = (i >> 1) * 4, e = (i & 1) * 2;
        const float y = (tq & 2) ? ((tq & 1) ? d[m4 + 3][e] : d[m4 + 2][e]) : ((tq & 1) ? d[m4 + 1][e] : d[m4][e]);
        st_relaxed(g_ypart + ((size_t)(warp * 16 + (m4 + tq) * 2 + (i & 1)) * NFFN + b) * 8 + g, tagf(y, tag));
      }
      PROF(8, ct == PT, 35); STAMP(14);
    }
    if (ct == 0) { sts2(par + PAR_CONST + 56, kwin, iwin); mbar_arrive(bar_win); }
    {
      const uint32_t mm0 = __shfl_sync(0xffffffffu, mm, ln & ~1), mm1 = __shfl_sync(0xffffffffu, mm, ln | 1);
      const uint32_t ih0 = __shfl_sync(0xffffffffu, ih, ln & ~1), ih1 = __shfl_sync(0xffffffffu, ih, ln | 1);
      const uint32_t il0 = __shfl_sync(0xffffffffu, il, ln & ~1), il1 = __shfl_sync(0xffffffffu, il, ln | 1);
      const bool mine = (iwin >> 4) == rb * 8 + warp;
#pragma unroll 1
      for (int hf = 0; hf < 2; hf++) {
        uint32_t x[16];
#pragma unroll
        for (int i = 0; i < 8; i += 2) ldmatrix4((trow ^ (i << 4)) + hf * 16384, x[2 * i], x[2 * i + 1], x[2 * i + 2], x[2 * i + 3]);
#pragma unroll
        for (int i = 0; i < 8; i++) {
          const uint4 pv = lds4(par + PAR_T2 + (hf * 8 + i) * 64 + tq * 16);
          x[2 * i] = hadd2(x[2 * i], hmul2(pv.z, ln_mod(x[2 * i], mm0, ih0, il0, pv.x, pv.y)));
          x[2 * i + 1] = hadd2(x[2 * i + 1], hmul2(pv.z, ln_mod(x[2 * i + 1], mm1, ih1, il1, pv.x, pv.y)));
        }
        if (mine) {
          uint32_t* dst = reinterpret_cast<uint32_t*>(P.out + (size_t)grow0 * DM + cj * 128 + hf * 64) + tq;
#pragma unroll
          for (int i = 0; i < 8; i++) {
            if (grow0 != iwin) dst[i * 4] = x[2 * i];
            if (grow0 + 8 != iwin) dst[i * 4 + 4 * DM] = x[2 * i + 1];
          }
        } else {
#pragma unroll
          for (int i = 0; i < 8; i += 2) stmatrix4((trow ^ (i << 4)) + hf * 16384, x[2 * i], x[2 * i + 1], x[2 * i + 2], x[2 * i + 3]);
          fence_async_smem();
          __syncwarp();
          if (elect_one()) {
            tma2d_store(&maps.out, res + hf * 16384 + warp * 2048, cj * 128 + hf * 64, rb * 128 + warp * 16);
            asm volatile("cp.async.bulk.commit_group;" ::: "memory");
          }
        }
      }
      asm volatile("cp.async.bulk.wait_group.read 0;" ::: "memory");
    }
    PROF(8, ct == PT, 11); STAMP(15);
    cluster_wait();
  }
}

typedef CUresult (*EncodeFn)(CUtensorMap*, CUtensorMapDataType, cuuint32_t, void*, const cuuint64_t*, const cuuint64_t*,
                             const cuuint32_t*, const cuuint32_t*, CUtensorMapInterleave, CUtensorMapSwizzle,
                             CUtensorMapL2promotion, CUtensorMapFloatOOBfill);

void map2d(EncodeFn enc, CUtensorMap* m, const void* p, uint64_t rows, uint64_t cols, uint32_t brows) {
  cuuint64_t dims[2] = {cols, rows}, strides[1] = {cols * 2};
  cuuint32_t box[2] = {64, brows}, es[2] = {1, 1};
  enc(m, CU_TENSOR_MAP_DATA_TYPE_BFLOAT16, 2, const_cast<void*>(p), dims, strides, box, es, CU_TENSOR_MAP_INTERLEAVE_NONE,
      CU_TENSOR_MAP_SWIZZLE_128B, CU_TENSOR_MAP_L2_PROMOTION_L2_256B, CU_TENSOR_MAP_FLOAT_OOB_FILL_NONE);
}
void map2d_narrow(EncodeFn enc, CUtensorMap* m, const void* p, uint64_t rows, uint64_t cols) {
  cuuint64_t dims[2] = {cols, rows}, strides[1] = {cols * 2};
  cuuint32_t box[2] = {32, 256}, es[2] = {1, 1};
  enc(m, CU_TENSOR_MAP_DATA_TYPE_BFLOAT16, 2, const_cast<void*>(p), dims, strides, box, es, CU_TENSOR_MAP_INTERLEAVE_NONE,
      CU_TENSOR_MAP_SWIZZLE_64B, CU_TENSOR_MAP_L2_PROMOTION_L2_64B, CU_TENSOR_MAP_FLOAT_OOB_FILL_NONE);
}
void map3d(EncodeFn enc, CUtensorMap* m, const void* p, uint64_t rows, uint64_t cols, uint32_t brows, uint32_t nch) {
  cuuint64_t dims[3] = {64, rows, cols / 64}, strides[2] = {cols * 2, 128};
  cuuint32_t box[3] = {64, brows, nch}, es[3] = {1, 1, 1};
  enc(m, CU_TENSOR_MAP_DATA_TYPE_BFLOAT16, 3, const_cast<void*>(p), dims, strides, box, es, CU_TENSOR_MAP_INTERLEAVE_NONE,
      CU_TENSOR_MAP_SWIZZLE_128B, CU_TENSOR_MAP_L2_PROMOTION_L2_256B, CU_TENSOR_MAP_FLOAT_OOB_FILL_NONE);
}

}

extern "C" void kernel_launch(void* const* d_in, const int* in_sizes, int n_in, void* d_out, int out_size) {
  (void)in_sizes; (void)n_in; (void)out_size;
  static EncodeFn enc = nullptr;
  if (!enc) {
    void* fn = nullptr;
    cudaDriverEntryPointQueryResult st;
    cudaGetDriverEntryPoint("cuTensorMapEncodeTiled", &fn, cudaEnableDefault, &st);
    enc = (EncodeFn)fn;
    cudaFuncSetAttribute(fused_kernel, cudaFuncAttributeMaxDynamicSharedMemorySize, SMEM_BYTES);
  }
  Maps maps;
  map2d(enc, &maps.x, d_in[0], SEQ, DM, 128);
  map2d(enc, &maps.out, d_out, SEQ, DM, 16);
  map3d(enc, &maps.wq, d_in[3], DM, NQ, 64, 2);
  map3d(enc, &maps.k, d_in[1], 4 * SK, 128, 128, 1);
  map3d(enc, &maps.v, d_in[2], 4 * SK, 128, 128, 1);
  map3d(enc, &maps.wo, d_in[4], NQ, DM, 64, 2);
  map2d_narrow(enc, &maps.wg, d_in[7], DM, FF);
  map2d_narrow(enc, &maps.wu, d_in[8], DM, FF);
  map3d(enc, &maps.wd, d_in[9], FF, DM, 32, 4);
  map2d_narrow(enc, &maps.wm, d_in[11], DM, NMOD);
  Ptrs p;
  p.x = (const __nv_bfloat16*)d_in[0];
  p.w_r = (const __nv_bfloat16*)d_in[6];
  p.w_gate = (const __nv_bfloat16*)d_in[7];
  p.w_up = (const __nv_bfloat16*)d_in[8];
  p.w_down = (const __nv_bfloat16*)d_in[9];
  p.c = (const __nv_bfloat16*)d_in[10];
  p.w_mod = (const __nv_bfloat16*)d_in[11];
  p.out = (__nv_bfloat16*)d_out;
  fused_kernel<<<NMAIN + NHELP, 384, SMEM_BYTES>>>(maps, p);
}
```

```cpp
#include <cuda_runtime.h>
#include <cuda_bf16.h>
#include <cuda.h>
#include <stdint.h>
#include <type_traits>

#define HD 1
#define HDX 2
#define XF 4
#define XE 32
#define XR 0
#define PF2 1
#define PF2T 4
#define NRS 6
#define FPACE 3
#define GOST 20
#define WB 2
#define WN 16
#define RES0 17
#define RES1 20
#define HU 32
#define NS1 6
#define PD0 12
#define PG0 31
#define VREL 7
#define E0 3

namespace {

constexpr int SEQ = 2048, DM = 1024, NQ = 4096, SK = 2048, WIN = 512, FF = 3584, NMOD = 6144;
constexpr int NMAIN = 128, NHELP = 4, NFFN = 112;
constexpr int NSLOT = 4, SLOT_BYTES = 32768, UNIT = 16384, GST_BYTES = 3 * UNIT;
constexpr uint32_t XT0 = 0x9630, XT1 = 0x54DC, XT2 = 0xDC96;
constexpr uint32_t WT0 = 0xA741, WT1 = 0x720A, WT2 = 0x20A7;
constexpr uint32_t AT0 = 0x7420, AT1 = 0x2C0A;
constexpr uint32_t QT = 0x549696DC;
constexpr int OFF_STAGE = 12 * UNIT;
constexpr uint32_t FT_G = 0x761B, FT_U = 0x0CA9, FT_D = 0x382D;
constexpr int OFF_RES = 4 * UNIT;
constexpr int OFF_PAR = 14 * UNIT;
constexpr int OFF_BAR = OFF_PAR + 2048 + 512;
constexpr int SMEM_BYTES = OFF_BAR + 512;
static_assert(SMEM_BYTES <= 232448, "smem");

constexpr int PAR_T1 = 0;
constexpr int PAR_T2 = 512;
constexpr int PAR_CONST = 1536;
constexpr int PAR_RED = 1600;
constexpr int PAR_SINK = 2176;

struct Maps {
  CUtensorMap x, wq, k, v, wo, wg, wu, wd, wm, out;
};
struct Ptrs {
  const __nv_bfloat16 *x, *w_r, *c, *w_mod, *w_gate, *w_up, *w_down;
  __nv_bfloat16* out;
};

__device__ __align__(1024) uint8_t g_act[16 * 80 * UNIT];
__device__ __align__(128) uint32_t g_mod[NMOD];
__device__ __align__(128) uint32_t g_modp[2 * 2 * DM];
__device__ __align__(128) uint32_t g_ln1[SEQ * 4];
__device__ __align__(128) uint32_t g_cnt_h[16 * 32];
__device__ __align__(128) uint32_t g_cnt_o[128 * 32];
__device__ __align__(128) uint32_t g_xch[NMAIN * 8 * 256 * 4];
__device__ __align__(128) uint32_t g_stats[8 * SEQ * 4];
__device__ __align__(128) uint32_t g_cand[NMAIN * 32];
__device__ __align__(128) uint32_t g_row[16 * 2 * DM];
__device__ __align__(128) uint32_t g_ypart[NMAIN * NFFN * 8];
__device__ uint32_t g_epoch;

__device__ __forceinline__ uint32_t fresh_lane() { uint32_t l; asm volatile("mov.u32 %0, %%laneid;" : "=r"(l)); return l; }
__device__ __forceinline__ uint32_t frag_offset(int warp) {
  const uint32_t l = fresh_lane();
  return ((warp & 3) * 16 + (l & 15)) * 128 + (((l >> 4) ^ (l & 7)) << 4);
}
__device__ __forceinline__ bool elect_one() {
  uint32_t p;
  asm volatile("{ .reg .pred q; elect.sync _|q, 0xffffffff; selp.u32 %0, 1, 0, q; }" : "=r"(p));
  return p;
}
__device__ __forceinline__ uint32_t smem_u32(const void* p) { return (uint32_t)__cvta_generic_to_shared(p); }
__device__ __forceinline__ void mbar_init(uint32_t bar, uint32_t cnt) {
  asm volatile("mbarrier.init.shared::cta.b64 [%0], %1;" ::"r"(bar), "r"(cnt) : "memory");
}
__device__ __forceinline__ void mbar_expect_tx(uint32_t bar, uint32_t bytes) {
  asm volatile("mbarrier.arrive.expect_tx.shared::cta.b64 _, [%0], %1;" ::"r"(bar), "r"(bytes) : "memory");
}
__device__ __forceinline__ void mbar_arrive(uint32_t bar) {
  asm volatile("mbarrier.arrive.shared::cta.b64 _, [%0];" ::"r"(bar) : "memory");
}
__device__ __forceinline__ void mbar_arrive_pred(uint32_t bar, bool p) {
  asm volatile("{ .reg .pred p; setp.ne.b32 p, %1, 0; @p mbarrier.arrive.shared::cta.b64 _, [%0]; }" ::"r"(bar), "r"((int)p) : "memory");
}
__device__ __forceinline__ void mbar_arrive_cl(uint32_t bar, uint32_t off, bool p = true) {
  asm volatile("{ .reg .pred p, q; .reg .b32 a; setp.ne.b32 q, %2, 0; setp.ne.and.b32 p, %0, 0, q; add.u32 a, %0, %1; @p mbarrier.arrive.shared::cluster.b64 _, [a]; }"
               ::"r"(bar), "r"(off), "r"((int)p) : "memory");
}
__device__ __forceinline__ uint32_t mapa(uint32_t addr, uint32_t cta) {
  uint32_t r; asm("mapa.shared::cluster.u32 %0, %1, %2;" : "=r"(r) : "r"(addr), "r"(cta)); return r;
}
__device__ __forceinline__ void cluster_arrive() { asm volatile("barrier.cluster.arrive.relaxed.aligned;" ::: "memory"); }
__device__ __forceinline__ void cluster_wait() { asm volatile("barrier.cluster.wait.aligned;" ::: "memory"); }
__device__ __forceinline__ void watchdog(uint32_t& n) {
}
__device__ __forceinline__ void mbar_wait(uint32_t bar, uint32_t parity) {
  asm volatile("{\n.reg .pred p;\nWAIT_%=:\nmbarrier.try_wait.parity.shared::cta.b64 p, [%0], %1;\n@!p bra WAIT_%=;\n}" ::"r"(bar), "r"(parity) : "memory");
}
__device__ __forceinline__ bool mbar_test(uint32_t bar, uint32_t parity) {
  uint32_t ok;
  asm volatile("{\n.reg .pred p;\nmbarrier.test_wait.parity.shared::cta.b64 p, [%1], %2;\nselp.u32 %0, 1, 0, p;\n}" : "=r"(ok) : "r"(bar), "r"(parity) : "memory");
  return ok;
}
__device__ __forceinline__ uint64_t l2_stream() {
  uint64_t f; asm("createpolicy.fractional.L2::evict_first.b64 %0, 1.0;" : "=l"(f)); return f;
}
__device__ __forceinline__ void tma2d(uint32_t dst, const CUtensorMap* m, int c0, int c1, uint32_t bar) {
  asm volatile("cp.async.bulk.tensor.2d.shared::cluster.global.mbarrier::complete_tx::bytes.L2::cache_hint [%0], [%1, {%3, %4}], [%2], %5;"
               ::"r"(dst), "l"(m), "r"(bar), "r"(c0), "r"(c1), "l"(l2_stream()) : "memory");
}
__device__ __forceinline__ void tma3d_prefetch(const CUtensorMap* m, int c0, int c1, int c2) {
  asm volatile("cp.async.bulk.prefetch.tensor.3d.L2.global.tile [%0, {%1, %2, %3}];" ::"l"(m), "r"(c0), "r"(c1), "r"(c2) : "memory");
}
__device__ __forceinline__ void bulk_load(uint32_t dst, const void* src, uint32_t bytes, uint32_t bar) {
  asm volatile("cp.async.bulk.shared::cluster.global.mbarrier::complete_tx::bytes [%0], [%1], %2, [%3];" ::"r"(dst), "l"(src), "r"(bytes), "r"(bar) : "memory");
}
__device__ __forceinline__ void bulk_load_stream(uint32_t dst, const void* src, uint32_t bytes, uint32_t bar) {
  asm volatile("cp.async.bulk.shared::cluster.global.mbarrier::complete_tx::bytes.L2::cache_hint [%0], [%1], %2, [%3], %4;"
               ::"r"(dst), "l"(src), "r"(bytes), "r"(bar), "l"(l2_stream()) : "memory");
}
__device__ __forceinline__ void tma2d_store(const CUtensorMap* m, uint32_t src, int c0, int c1) {
  asm volatile("cp.async.bulk.tensor.2d.global.shared::cta.bulk_group [%0, {%2, %3}], [%1];" ::"l"(m), "r"(src), "r"(c0), "r"(c1) : "memory");
}
__device__ __forceinline__ void bulk_store(void* dst, uint32_t src, uint32_t bytes) {
  asm volatile("cp.async.bulk.global.shared::cta.bulk_group [%0], [%1], %2;" ::"l"(dst), "r"(src), "r"(bytes) : "memory");
}
__device__ __forceinline__ uint32_t unit_of(uint32_t table, uint32_t i) { return ((table >> (i * 4)) & 15) * UNIT; }
__device__ __forceinline__ void tma3d(uint32_t dst, const CUtensorMap* m, int c0, int c1, int c2, uint32_t bar) {
  asm volatile("cp.async.bulk.tensor.3d.shared::cluster.global.mbarrier::complete_tx::bytes.L2::cache_hint [%0], [%1, {%3, %4, %5}], [%2], %6;"
               ::"r"(dst), "l"(m), "r"(bar), "r"(c0), "r"(c1), "r"(c2), "l"(l2_stream()) : "memory");
}
template <bool STREAM>
__device__ __forceinline__ void tma3d_mc(uint32_t dst, const CUtensorMap* m, int c0, int c1, int c2, uint32_t bar) {
  if (STREAM)
    asm volatile("cp.async.bulk.tensor.3d.shared::cluster.global.mbarrier::complete_tx::bytes.multicast::cluster.L2::cache_hint [%0], [%1, {%3, %4, %5}], [%2], %6, %7;"
                 ::"r"(dst), "l"(m), "r"(bar), "r"(c0), "r"(c1), "r"(c2), "h"((uint16_t)3), "l"(l2_stream()) : "memory");
  else
    asm volatile("cp.async.bulk.tensor.3d.shared::cluster.global.mbarrier::complete_tx::bytes.multicast::cluster [%0], [%1, {%3, %4, %5}], [%2], %6;"
                 ::"r"(dst), "l"(m), "r"(bar), "r"(c0), "r"(c1), "r"(c2), "h"((uint16_t)3) : "memory");
}
__device__ __forceinline__ void prefetch_map(const CUtensorMap* m) {
  asm volatile("prefetch.tensormap [%0];" ::"l"(m) : "memory");
}
__device__ __forceinline__ void fence_async() { asm volatile("fence.proxy.async.global;" ::: "memory"); }
__device__ __forceinline__ void fence_async_smem() { asm volatile("fence.proxy.async.shared::cta;" ::: "memory"); }
__device__ __forceinline__ void bar_sync(int id, int n) { asm volatile("bar.sync %0, %1;" ::"r"(id), "r"(n) : "memory"); }
__device__ __forceinline__ void bar_arrive(int id, int n) { asm volatile("bar.arrive %0, %1;" ::"r"(id), "r"(n) : "memory"); }
__device__ __forceinline__ void wg_fence() { asm volatile("wgmma.fence.sync.aligned;" ::: "memory"); }
__device__ __forceinline__ void wg_commit() { asm volatile("wgmma.commit_group.sync.aligned;" ::: "memory"); }
template <int N> __device__ __forceinline__ void wg_wait() { asm volatile("wgmma.wait_group.sync.aligned %0;" ::"n"(N) : "memory"); }
__device__ __forceinline__ uint64_t make_desc(uint32_t addr, uint32_t lbo, uint32_t sbo) {
  return (uint64_t)((addr & 0x3FFFF) >> 4) | ((uint64_t)(lbo >> 4) << 16) | ((uint64_t)(sbo >> 4) << 32) | (1ull << 62);
}
__device__ __forceinline__ uint32_t ld_relaxed(const uint32_t* p) {
  uint32_t v; asm volatile("ld.relaxed.gpu.global.u32 %0, [%1];" : "=r"(v) : "l"(p) : "memory"); return v;
}
__device__ __forceinline__ uint32_t ld_acquire(const uint32_t* p) {
  uint32_t v; asm volatile("ld.acquire.gpu.global.u32 %0, [%1];" : "=r"(v) : "l"(p) : "memory"); return v;
}
__device__ __forceinline__ uint4 ld_relaxed4(const uint32_t* p) {
  uint4 v; asm volatile("ld.relaxed.gpu.global.v4.u32 {%0,%1,%2,%3}, [%4];" : "=r"(v.x), "=r"(v.y), "=r"(v.z), "=r"(v.w) : "l"(p) : "memory"); return v;
}
__device__ __forceinline__ uint2 ld_relaxed2(const uint32_t* p) {
  uint2 v; asm volatile("ld.relaxed.gpu.global.v2.u32 {%0,%1}, [%2];" : "=r"(v.x), "=r"(v.y) : "l"(p) : "memory"); return v;
}
__device__ __forceinline__ void st_relaxed(uint32_t* p, uint32_t v) {
  asm volatile("st.relaxed.gpu.global.u32 [%0], %1;" ::"l"(p), "r"(v) : "memory");
}
__device__ __forceinline__ void st_relaxed2(uint32_t* p, uint32_t a, uint32_t b) {
  asm volatile("st.relaxed.gpu.global.v2.u32 [%0], {%1,%2};" ::"l"(p), "r"(a), "r"(b) : "memory");
}
__device__ __forceinline__ void st_relaxed4(uint32_t* p, uint32_t a, uint32_t b, uint32_t c, uint32_t d) {
  asm volatile("st.relaxed.gpu.global.v4.u32 [%0], {%1,%2,%3,%4};" ::"l"(p), "r"(a), "r"(b), "r"(c), "r"(d) : "memory");
}
__device__ __forceinline__ void st_b128(uint32_t* p, uint32_t a, uint32_t b, uint32_t c, uint32_t d) {
  asm volatile("{ .reg .b64 u, v; .reg .b128 w; mov.b64 u, {%1, %2}; mov.b64 v, {%3, %4}; mov.b128 w, {u, v}; st.relaxed.gpu.global.b128 [%0], w; }"
               ::"l"(p), "r"(a), "r"(b), "r"(c), "r"(d) : "memory");
}
__device__ __forceinline__ uint4 ld_b128(const uint32_t* p) {
  uint4 r;
  asm volatile("{ .reg .b64 u, v; .reg .b128 w; ld.relaxed.gpu.global.b128 w, [%4]; mov.b128 {u, v}, w; mov.b64 {%0, %1}, u; mov.b64 {%2, %3}, v; }"
               : "=r"(r.x), "=r"(r.y), "=r"(r.z), "=r"(r.w) : "l"(p) : "memory");
  return r;
}
__device__ __forceinline__ void st_pairs(uint32_t* p, uint32_t a, uint32_t b, uint32_t tag) {
  asm volatile("{ .reg .b64 u, v; mov.b64 u, {%1, %3}; mov.b64 v, {%2, %3}; st.relaxed.gpu.global.v2.b64 [%0], {u, v}; }"
               ::"l"(p), "r"(a), "r"(b), "r"(tag) : "memory");
}
__device__ __forceinline__ uint4 ld_pairs(const uint32_t* p) {
  uint4 v;
  asm volatile("{ .reg .b64 u, v; ld.relaxed.gpu.global.v2.b64 {u, v}, [%4]; mov.b64 {%0, %1}, u; mov.b64 {%2, %3}, v; }"
               : "=r"(v.x), "=r"(v.y), "=r"(v.z), "=r"(v.w) : "l"(p) : "memory");
  return v;
}
__device__ __forceinline__ uint2 ld_pair(const uint32_t* p) {
  uint2 v;
  asm volatile("{ .reg .b64 u; ld.relaxed.gpu.global.b64 u, [%2]; mov.b64 {%0, %1}, u; }" : "=r"(v.x), "=r"(v.y) : "l"(p) : "memory");
  return v;
}
__device__ __forceinline__ void red_release(uint32_t* p, uint32_t v) {
  asm volatile("red.release.gpu.global.add.u32 [%0], %1;" ::"l"(p), "r"(v) : "memory");
}
__device__ __forceinline__ uint32_t ldg_nc1(const void* p) {
  uint32_t v;
  asm volatile("ld.global.nc.u32 %0, [%1];" : "=r"(v) : "l"(p));
  return v;
}
__device__ __forceinline__ uint4 ldg_nc4(const void* p) {
  uint4 v; asm volatile("ld.global.nc.L1::no_allocate.v4.u32 {%0,%1,%2,%3}, [%4];" : "=r"(v.x), "=r"(v.y), "=r"(v.z), "=r"(v.w) : "l"(p)); return v;
}
__device__ __forceinline__ uint4 ldg_stream4(const void* p) {
  uint4 v;
  asm volatile("ld.global.nc.L1::no_allocate.L2::cache_hint.v4.u32 {%0,%1,%2,%3}, [%4], %5;" : "=r"(v.x), "=r"(v.y), "=r"(v.z), "=r"(v.w) : "l"(p), "l"(l2_stream()));
  return v;
}
__device__ __forceinline__ void stg4(void* p, uint4 v) {
  asm volatile("st.global.v4.u32 [%0], {%1,%2,%3,%4};" ::"l"(p), "r"(v.x), "r"(v.y), "r"(v.z), "r"(v.w) : "memory");
}
__device__ __forceinline__ void wait_counter(const uint32_t* p, uint32_t target) {
  uint32_t n = 0;
  while ((int)(ld_acquire(p) - target) < 0) { watchdog(n); }
}
__device__ __forceinline__ uint32_t tagf(float v, uint32_t tag) { return (__float_as_uint(v) & ~3u) | tag; }
__device__ __forceinline__ bool tag_ok(uint4 v, uint32_t tag) { return (((v.x ^ tag) | (v.y ^ tag) | (v.z ^ tag) | (v.w ^ tag)) & 3u) == 0; }
__device__ __forceinline__ float untag_sum(uint32_t a, uint32_t b) { return __uint_as_float(a & ~3u) + __uint_as_float(b & ~3u); }
__device__ __forceinline__ uint4 poll4(const uint32_t* p, uint32_t tag) {
  uint4 v = ld_relaxed4(p);
  uint32_t n = 0;
  while (!tag_ok(v, tag)) { v = ld_relaxed4(p); watchdog(n); }
  return v;
}
__device__ __forceinline__ float bf_lo(uint32_t v) { return __uint_as_float(v << 16); }
__device__ __forceinline__ float bf_hi(uint32_t v) { return __uint_as_float(v & 0xffff0000u); }
__device__ __forceinline__ uint32_t pack_bf(float lo, float hi) {
  uint32_t r; asm("cvt.rn.bf16x2.f32 %0, %1, %2;" : "=r"(r) : "f"(hi), "f"(lo)); return r;
}
__device__ __forceinline__ float rbf(float v) { return __uint_as_float(pack_bf(0.f, v) & 0xffff0000u); }
__device__ __forceinline__ uint32_t hmul2(uint32_t a, uint32_t b) {
  uint32_t r; asm("mul.rn.bf16x2 %0, %1, %2;" : "=r"(r) : "r"(a), "r"(b)); return r;
}
__device__ __forceinline__ uint32_t hadd2(uint32_t a, uint32_t b) {
  uint32_t r; asm("add.rn.bf16x2 %0, %1, %2;" : "=r"(r) : "r"(a), "r"(b)); return r;
}
__device__ __forceinline__ uint32_t hsub2(uint32_t a, uint32_t b) {
  uint32_t r; asm("sub.rn.bf16x2 %0, %1, %2;" : "=r"(r) : "r"(a), "r"(b)); return r;
}
__device__ __forceinline__ uint32_t hmax2(uint32_t a, uint32_t b) {
  uint32_t r; asm("max.bf16x2 %0, %1, %2;" : "=r"(r) : "r"(a), "r"(b)); return r;
}
__device__ __forceinline__ float rcp(float x) { float r; asm("rcp.approx.ftz.f32 %0, %1;" : "=f"(r) : "f"(x)); return r; }
__device__ __forceinline__ float ex2(float x) { float r; asm("ex2.approx.ftz.f32 %0, %1;" : "=f"(r) : "f"(x)); return r; }
__device__ __forceinline__ void stmatrix4(uint32_t addr, uint32_t a, uint32_t b, uint32_t c, uint32_t d) {
  asm volatile("stmatrix.sync.aligned.m8n8.x4.shared.b16 [%0], {%1,%2,%3,%4};" ::"r"(addr), "r"(a), "r"(b), "r"(c), "r"(d) : "memory");
}
__device__ __forceinline__ void ldmatrix4(uint32_t addr, uint32_t& a, uint32_t& b, uint32_t& c, uint32_t& d) {
  asm volatile("ldmatrix.sync.aligned.m8n8.x4.shared.b16 {%0,%1,%2,%3}, [%4];" : "=r"(a), "=r"(b), "=r"(c), "=r"(d) : "r"(addr) : "memory");
}
__device__ __forceinline__ void ldmatrix4t(uint32_t addr, uint32_t& a, uint32_t& b, uint32_t& c, uint32_t& d) {
  asm volatile("ldmatrix.sync.aligned.m8n8.x4.trans.shared.b16 {%0,%1,%2,%3}, [%4];" : "=r"(a), "=r"(b), "=r"(c), "=r"(d) : "r"(addr) : "memory");
}
__device__ __forceinline__ void mma16816(float (&d)[4], uint32_t a0, uint32_t a1, uint32_t a2, uint32_t a3, uint32_t b0, uint32_t b1) {
  asm volatile("mma.sync.aligned.m16n8k16.row.col.f32.bf16.bf16.f32 {%0,%1,%2,%3}, {%4,%5,%6,%7}, {%8,%9}, {%0,%1,%2,%3};"
               : "+f"(d[0]), "+f"(d[1]), "+f"(d[2]), "+f"(d[3]) : "r"(a0), "r"(a1), "r"(a2), "r"(a3), "r"(b0), "r"(b1));
}
__device__ __forceinline__ void sts1(uint32_t a, uint32_t v) { asm volatile("st.shared.u32 [%0], %1;" ::"r"(a), "r"(v) : "memory"); }
__device__ __forceinline__ uint4 lds4(uint32_t a) {
  uint4 v; asm volatile("ld.shared.v4.u32 {%0,%1,%2,%3}, [%4];" : "=r"(v.x), "=r"(v.y), "=r"(v.z), "=r"(v.w) : "r"(a) : "memory"); return v;
}
__device__ __forceinline__ uint2 lds2(uint32_t a) {
  uint2 v; asm volatile("ld.shared.v2.u32 {%0,%1}, [%2];" : "=r"(v.x), "=r"(v.y) : "r"(a) : "memory"); return v;
}
__device__ __forceinline__ uint32_t lds1(uint32_t a) {
  uint32_t v; asm volatile("ld.shared.u32 %0, [%1];" : "=r"(v) : "r"(a) : "memory"); return v;
}
__device__ __forceinline__ void sts2(uint32_t a, uint32_t x, uint32_t y) { asm volatile("st.shared.v2.u32 [%0], {%1,%2};" ::"r"(a), "r"(x), "r"(y) : "memory"); }
__device__ __forceinline__ void sts4(uint32_t a, uint4 v) {
  asm volatile("st.shared.v4.u32 [%0], {%1,%2,%3,%4};" ::"r"(a), "r"(v.x), "r"(v.y), "r"(v.z), "r"(v.w) : "memory");
}
__device__ __forceinline__ float silu_f(float v) { return __fdividef(v, 1.f + __expf(-v)); }
__device__ __forceinline__ uint32_t hfma2(uint32_t a, uint32_t b, uint32_t c) {
  uint32_t r; asm("fma.rn.bf16x2 %0, %1, %2, %3;" : "=r"(r) : "r"(a), "r"(b), "r"(c)); return r;
}
__device__ __forceinline__ void split_inv(float sd, uint32_t& ih, uint32_t& il) {
  const float inv = rcp(sd);
  ih = pack_bf(inv, inv);
  const float lo = inv - bf_lo(ih);
  il = pack_bf(lo, lo);
}
__device__ __forceinline__ uint32_t ln_mod(uint32_t x, uint32_t mean2, uint32_t ih, uint32_t il, uint32_t c1, uint32_t sh) {
  const uint32_t d = hsub2(x, mean2);
  return hadd2(hmul2(hfma2(d, ih, hmul2(d, il)), c1), sh);
}

#define R8(a, i) "+f"(a[i]), "+f"(a[i + 1]), "+f"(a[i + 2]), "+f"(a[i + 3]), "+f"(a[i + 4]), "+f"(a[i + 5]), "+f"(a[i + 6]), "+f"(a[i + 7])
#define D64 "{%0,%1,%2,%3,%4,%5,%6,%7,%8,%9,%10,%11,%12,%13,%14,%15,%16,%17,%18,%19,%20,%21,%22,%23,%24,%25,%26,%27,%28,%29,%30,%31," \
            "%32,%33,%34,%35,%36,%37,%38,%39,%40,%41,%42,%43,%44,%45,%46,%47,%48,%49,%50,%51,%52,%53,%54,%55,%56,%57,%58,%59,%60,%61,%62,%63}"
template <int TB>
__device__ __forceinline__ void mma_ss(float (&d)[64], uint64_t da, uint64_t db, int sc) {
  asm volatile("{\n.reg .pred p;\nsetp.ne.b32 p, %66, 0;\n"
               "wgmma.mma_async.sync.aligned.m64n128k16.f32.bf16.bf16 " D64 ", %64, %65, p, 1, 1, 0, %67;\n}"
               : R8(d, 0), R8(d, 8), R8(d, 16), R8(d, 24), R8(d, 32), R8(d, 40), R8(d, 48), R8(d, 56)
               : "l"(da), "l"(db), "r"(sc), "n"(TB));
}
template <int TB>
__device__ __forceinline__ void mma_rs(float (&d)[64], uint32_t a0, uint32_t a1, uint32_t a2, uint32_t a3, uint64_t db, int sc) {
  asm volatile("{\n.reg .pred p;\nsetp.ne.b32 p, %69, 0;\n"
               "wgmma.mma_async.sync.aligned.m64n128k16.f32.bf16.bf16 " D64 ", {%64,%65,%66,%67}, %68, p, 1, 1, %70;\n}"
               : R8(d, 0), R8(d, 8), R8(d, 16), R8(d, 24), R8(d, 32), R8(d, 40), R8(d, 48), R8(d, 56)
               : "r"(a0), "r"(a1), "r"(a2), "r"(a3), "l"(db), "r"(sc), "n"(TB));
}
#define D128 "{%0,%1,%2,%3,%4,%5,%6,%7,%8,%9,%10,%11,%12,%13,%14,%15,%16,%17,%18,%19,%20,%21,%22,%23,%24,%25,%26,%27,%28,%29,%30,%31," \
             "%32,%33,%34,%35,%36,%37,%38,%39,%40,%41,%42,%43,%44,%45,%46,%47,%48,%49,%50,%51,%52,%53,%54,%55,%56,%57,%58,%59,%60,%61,%62,%63," \
             "%64,%65,%66,%67,%68,%69,%70,%71,%72,%73,%74,%75,%76,%77,%78,%79,%80,%81,%82,%83,%84,%85,%86,%87,%88,%89,%90,%91,%92,%93,%94,%95," \
             "%96,%97,%98,%99,%100,%101,%102,%103,%104,%105,%106,%107,%108,%109,%110,%111,%112,%113,%114,%115,%116,%117,%118,%119,%120,%121,%122,%123,%124,%125,%126,%127}"
#define R128(d, e) R8(d, 0), R8(d, 8), R8(d, 16), R8(d, 24), R8(d, 32), R8(d, 40), R8(d, 48), R8(d, 56), \
                   R8(e, 0), R8(e, 8), R8(e, 16), R8(e, 24), R8(e, 32), R8(e, 40), R8(e, 48), R8(e, 56)
__device__ __forceinline__ void mma256_ss(float (&d)[64], float (&e)[64], uint64_t da, uint64_t db, int sc) {
  asm volatile("{\n.reg .pred p;\nsetp.ne.b32 p, %130, 0;\n"
               "wgmma.mma_async.sync.aligned.m64n256k16.f32.bf16.bf16 " D128 ", %128, %129, p, 1, 1, 0, 1;\n}"
               : R128(d, e) : "l"(da), "l"(db), "r"(sc));
}
__device__ __forceinline__ void mma256_rs(float (&d)[64], float (&e)[64], uint32_t a0, uint32_t a1, uint32_t a2, uint32_t a3, uint64_t db) {
  asm volatile("{\n.reg .pred p;\nsetp.ne.b32 p, 1, 0;\n"
               "wgmma.mma_async.sync.aligned.m64n256k16.f32.bf16.bf16 " D128 ", {%128,%129,%130,%131}, %132, p, 1, 1, 1;\n}"
               : R128(d, e) : "r"(a0), "r"(a1), "r"(a2), "r"(a3), "l"(db));
}
template <int N> __device__ __forceinline__ void keep(float (&a)[N]) {
#pragma unroll
  for (int i = 0; i < N; i++) asm volatile("" : "+f"(a[i])::"memory");
}
template <int N> __device__ __forceinline__ void keep(uint32_t (&a)[N]) {
#pragma unroll
  for (int i = 0; i < N; i++) asm volatile("" : "+r"(a[i])::"memory");
}

#define STAMP(idx) do {} while (0)
#define PROF(grp, cond, idx) do {} while (0)

constexpr float SCL2 = 1.4426950408889634f * 0.08838834764831845f;

__device__ __forceinline__ void pack_p(const float (&s)[64], uint32_t (&p)[32]) {
#pragma unroll
  for (int i = 0; i < 32; i++) p[i] = pack_bf(s[2 * i], s[2 * i + 1]);
}

__device__ __forceinline__ void issue_qk(float (&s)[64], uint32_t q0, uint32_t q1, uint32_t kslot) {
  const uint64_t db = make_desc(kslot, 16, 1024), da0 = make_desc(q0, 16, 1024), da1 = make_desc(q1, 16, 1024);
#pragma unroll
  for (int kk = 0; kk < 8; kk++) mma_ss<0>(s, (kk < 4 ? da0 : da1) + (kk & 3) * 2, db + (kk >> 2) * 1024 + (kk & 3) * 2, kk != 0);
}
__device__ __forceinline__ void issue_pv(float (&o)[64], uint32_t (&p)[32], uint32_t vslot, int acc) {
  uint64_t db = make_desc(vslot, 16384, 1024);
#pragma unroll
  for (int kk = 0; kk < 8; kk++)
    mma_rs<1>(o, p[4 * kk], p[4 * kk + 1], p[4 * kk + 2], p[4 * kk + 3], db + kk * 128, kk == 0 ? acc : 1);
}

template <int H>
__device__ __forceinline__ void store_chunk(const float (&a)[64], uint32_t addr) {
#pragma unroll
  for (int i = 8 * H; i < 8 * H + 8; i += 2)
    stmatrix4(addr ^ ((i & 7) << 4), pack_bf(a[4 * i], a[4 * i + 1]), pack_bf(a[4 * i + 2], a[4 * i + 3]),
              pack_bf(a[4 * i + 4], a[4 * i + 5]), pack_bf(a[4 * i + 6], a[4 * i + 7]));
}
template <int H>
__device__ __forceinline__ void store_chunk(const float (&a)[64], float i0, float i1, uint32_t addr) {
#pragma unroll
  for (int i = 8 * H; i < 8 * H + 8; i += 2)
    stmatrix4(addr ^ ((i & 7) << 4), pack_bf(a[4 * i] * i0, a[4 * i + 1] * i0), pack_bf(a[4 * i + 2] * i1, a[4 * i + 3] * i1),
              pack_bf(a[4 * i + 4] * i0, a[4 * i + 5] * i0), pack_bf(a[4 * i + 6] * i1, a[4 * i + 7] * i1));
}
__device__ __forceinline__ float inv_quad_sum(float l) {
  l += __shfl_xor_sync(0xffffffffu, l, 1);
  l += __shfl_xor_sync(0xffffffffu, l, 2);
  return rcp(l);
}

__device__ __forceinline__ void ln_scalars(float mean, float var, float& mb, float& sd) {
  mb = rbf(mean);
  float r; asm("sqrt.approx.ftz.f32 %0, %1;" : "=f"(r) : "f"(rbf(rbf(var) + 1e-5f)));
  sd = rbf(r);
}

__global__ void __cluster_dims__(2, 1, 1) __launch_bounds__(384, 1) fused_kernel(const __grid_constant__ Maps maps, const Ptrs P) {
  extern __shared__ __align__(1024) uint8_t smem_raw[];
  const uint32_t base = smem_u32(smem_raw);
  const int tid = threadIdx.x, lane = tid & 31;
  const int warp = __shfl_sync(0xffffffffu, tid >> 5, 0);
  const int b = blockIdx.x;
  PROF(31, tid == 0, 0);

  if (b >= NMAIN) {
    float* sc = reinterpret_cast<float*>(smem_raw);
    float* red = sc + DM;
    for (int k = tid; k < DM; k += 384) sc[k] = rbf(silu_f(__bfloat162float(P.c[k])));
    __syncthreads();
    if (tid < 256) {
      const int col = 2048 + (b - NMAIN) * 1024 + (tid & 127) * 8, r0 = (tid >> 7) * 512;
      float acc[8];
#pragma unroll
      for (int e = 0; e < 8; e++) acc[e] = 0.f;
#pragma unroll 1
      for (int r = r0; r < r0 + 512; r += HU) {
        uint4 w[HU];
#pragma unroll
        for (int u = 0; u < HU; u++) w[u] = ldg_stream4(P.w_mod + (size_t)(r + u) * NMOD + col);
#pragma unroll
        for (int u = 0; u < HU; u++) {
          float s = sc[r + u];
          acc[0] += s * bf_lo(w[u].x); acc[1] += s * bf_hi(w[u].x); acc[2] += s * bf_lo(w[u].y); acc[3] += s * bf_hi(w[u].y);
          acc[4] += s * bf_lo(w[u].z); acc[5] += s * bf_hi(w[u].z); acc[6] += s * bf_lo(w[u].w); acc[7] += s * bf_hi(w[u].w);
        }
      }
      if (tid >= 128) {
#pragma unroll
        for (int e = 0; e < 8; e++) red[(tid & 127) * 8 + e] = acc[e];
      }
      const uint32_t tag = ld_relaxed(&g_epoch) % 3 + 1;
      bar_sync(1, 256);
      if (tid < 128) {
        uint32_t o[8];
#pragma unroll
        for (int e = 0; e < 8; e++) o[e] = __float_as_uint(rbf(acc[e] + red[tid * 8 + e])) | tag;
        st_relaxed4(g_mod + col, o[0], o[1], o[2], o[3]);
        st_relaxed4(g_mod + col + 4, o[4], o[5], o[6], o[7]);
        const uint4 wr = ldg_nc4(P.w_r + tid * 8);
        const uint32_t wv[4] = {wr.x, wr.y, wr.z, wr.w};
        float dsum = 0.f;
#pragma unroll
        for (int e = 0; e < 8; e++) {
          const float m = bf_hi(o[e]);
          dsum += (b == NMAIN + 2 ? rbf(1.f + m) : m) * ((e & 1) ? bf_hi(wv[e >> 1]) : bf_lo(wv[e >> 1]));
        }
#pragma unroll
        for (int k = 16; k > 0; k >>= 1) dsum += __shfl_xor_sync(0xffffffffu, dsum, k);
        if (lane == 0) st_relaxed(g_mod + (b - NMAIN) * 4 + warp, tagf(dsum, tag));
      }
    }
    PROF(2, tid == 0, 1);
    return;
  }

  const int rank = b & 1;
  const int rb = ((b >> 4) << 1) | rank, cj = (b >> 1) & 7;
  const uint32_t bfull = base + OFF_BAR, bempty = bfull + NSLOT * 8;
  const uint32_t gfull = bempty + NSLOT * 8, gempty = gfull + 32;
  const uint32_t bar_ofull = gempty + 32;
  const uint32_t bar_ofree = bar_ofull + 16;
  const uint32_t bar_par = bar_ofree + 32;
  const uint32_t bar_mod = bar_par + 8;
  const uint32_t bar_pread = bar_mod + 8;
  const uint32_t bar_xres = bar_pread + 8;
  const uint32_t bar_ring = bar_xres + 8;
  const uint32_t bar_box = bar_ring + 24;
  const uint32_t bar_go = bar_box + 96;
  const uint32_t bar_go2 = bar_go + 16;
  const uint32_t bar_cnt = bar_go + 24;
  const uint32_t xfull = bar_go + 32, xempty = xfull + 32;
  const uint32_t bar_hw = xempty + 32, bar_hx = bar_hw + 8;
  const uint32_t bar_hpub = bar_hx + 16;
  const uint32_t bar_win = bar_hpub + 8;
  const uint32_t bar_rx = bar_win + 8;
  const uint32_t bar_res = bar_go + 8;
  const uint32_t stage = base + OFF_STAGE, par = base + OFF_PAR;

  if (warp == 8 && elect_one()) {
    for (int s = 0; s < NSLOT; s++) { mbar_init(bfull + s * 8, 1); mbar_init(bempty + s * 8, 16); }
    for (int s = 0; s < 4; s++) { mbar_init(gfull + s * 8, 1); mbar_init(gempty + s * 8, 16); mbar_init(xfull + s * 8, 1); mbar_init(xempty + s * 8, 8); mbar_init(bar_ofree + s * 8, 1); }
    mbar_init(bar_ofull, 128); mbar_init(bar_ofull + 8, 128);
    mbar_init(bar_par, 64); mbar_init(bar_mod, 256); mbar_init(bar_pread, 8); mbar_init(bar_xres, 1);
    mbar_init(bar_ring, 8); mbar_init(bar_ring + 8, 8); mbar_init(bar_ring + 16, 8);
    mbar_init(bar_go, 1); mbar_init(bar_go2, 1); mbar_init(bar_cnt, 1); mbar_init(bar_hpub, 8); mbar_init(bar_res, 1); mbar_init(bar_win, 1); mbar_init(bar_rx, 1);
    for (int s = 0; s < 12; s++) mbar_init(bar_box + s * 8, 1);
    asm volatile("fence.mbarrier_init.release.cluster;" ::: "memory");
    prefetch_map(&maps.x); prefetch_map(&maps.wq); prefetch_map(&maps.k); prefetch_map(&maps.v);
  }
  if (warp == 9 && elect_one()) {
    mbar_init(bar_hw, 1); mbar_init(bar_hx, 1); mbar_init(bar_hx + 8, 1);
    asm volatile("fence.mbarrier_init.release.cluster;" ::: "memory");
    mbar_expect_tx(bar_hw, 32768);
    mbar_expect_tx(bar_hx, 16384);
    mbar_expect_tx(bar_hx + 8, 16384);
    const __nv_bfloat16* xs = P.x + (size_t)(rb * 128 + cj * 16) * DM;
    bulk_load(base + 2 * GST_BYTES, xs, 16384, bar_hx);
    tma2d(stage, &maps.wm, (b >> 1) * 32, rank * 512, bar_hw);
    tma2d(stage + 16384, &maps.wm, (b >> 1) * 32, rank * 512 + 256, bar_hw);
    bulk_load(base + 3 * GST_BYTES, xs + 8 * DM, 16384, bar_hx + 8);
  }
  cluster_arrive();

  if (warp >= 8) {
    asm volatile("setmaxnreg.dec.sync.aligned.u32 40;");
    if (warp < 10) bar_arrive(1, 320);
    const uint32_t epoch = ld_relaxed(&g_epoch);
    cluster_wait();
    if (warp == 8) {
      const int kvrow = (cj >> 1) * SK + (SK - WIN);
      int wch = cj * 8 + rank * 2;
#pragma unroll 1
      for (int ps = 0; ps < 3; ps++) {
        const CUtensorMap* mw = ps == 2 ? &maps.wo : &maps.wq;
        const uint32_t xt = ps == 1 ? XT1 : XT2, wt = ps == 0 ? WT0 : (ps == 1 ? WT1 : WT2);
        const int nst = ps == 2 ? 32 : 16;
        if (ps) {
          mbar_wait(bar_ofree + (ps - 1) * 16, 0);
          fence_async();
        }
#pragma unroll 1
        for (int i = 0; i < nst; i++) {
          const uint32_t bf = gfull + (i & 3) * 8;
          const int kt = ps == 2 ? (((cj & 1) * 4 + ((i >> 1) & 3)) * 4 + (i >> 3)) * 2 + (i & 1) : (i + (ps ? 0 : b & 14)) & 15;
          const uint32_t wd = base + unit_of(wt, i & 3) + rank * UNIT, xd = base + unit_of(xt, i & 3);
          const uint8_t* xs = g_act + (uint32_t)(rb * 80 + (ps - 1) * 16 + kt) * UNIT;
          if (ps == 0 && i == HD) mbar_wait(bar_mod, 0);
          if (ps && i && i < 4) mbar_wait(bempty + (i == 3 ? 3 : i - 1) * 8, 1);
          mbar_wait(gempty + (i & 3) * 8, ((i >> 2) & 1) ^ 1);
          if (elect_one()) {
            mbar_expect_tx(bf, ps ? GST_BYTES : 2 * UNIT);
            tma3d_mc<true>(wd, mw, 0, (i == 31 ? kt ^ (rank * 32) : kt) * 64, i == 31 ? cj * 2 : wch, bf);
          }
          if (ps) {
            if (i == 16) mbar_wait(bar_cnt, 0);
            if (i == 2) mbar_wait(bempty + 16, 1);
            if (elect_one()) {
              bulk_load_stream(xd, xs, UNIT, bf);
              mbar_arrive_pred(bar_go, i == GOST - 1);
              mbar_arrive_pred(bar_go2, ps * 16 + i == PG0);
              mbar_arrive_pred(bar_res, ((1u << RES0 | 1u << RES1) >> i) & 1);
              if (ps == 2 && b < NFFN && i >= PD0 && i < PD0 + 16)
                asm volatile("cp.async.bulk.prefetch.L2.global [%0], 4096;" ::"l"(P.w_down + (size_t)b * 32768 + (i - PD0) * 2048) : "memory");
            }
          }
        }
        if (ps == 2) break;
        wch = ps ? ((wch >> 3) ^ rank) * 2 : wch + 4;
#pragma unroll 1
        for (int u = 0; u < 16; u++) {
          const bool isk = (u == 0) || ((u & 1) && u < 15);
          const int blk = (isk ? (u + 1) >> 1 : (u == 15 ? 7 : (u >> 1) - 1)) & 3;
          const uint32_t sl = base + unit_of(ps ? AT1 : AT0, u & 3) + rank * UNIT, bf = bfull + (u & 3) * 8;
          if (u < 4) mbar_wait(gempty + ((u + 1) >> 1) * 8, 1);
          mbar_wait(bempty + (u & 3) * 8, ((u >> 2) & 1) ^ 1);
          if (elect_one()) {
            mbar_expect_tx(bf, SLOT_BYTES);
            tma3d_mc<false>(sl, isk ? &maps.k : &maps.v, 0, kvrow + blk * 128, rank, bf);
            if (ps && u >= PF2T && u < PF2T + 2 * PF2 && !((u - PF2T) & 1))
              tma3d_prefetch(&maps.wo, 0, ((((cj & 1) * 4 + (b >> 5)) * 4 + ((u - PF2T) >> 1)) * 2 + ((b >> 4) & 1)) * 64, (cj ^ rank) * 2);
          }
        }
      }
      mbar_wait(bar_ring, 0);
      if (elect_one()) {
        mbar_expect_tx(bar_rx, UNIT);
        bulk_load_stream(base + 8 * UNIT, g_act + (uint32_t)(rb * 80 + 16 + 63 - (cj & 1) * 32) * UNIT, UNIT, bar_rx);
      }
      if (b < NFFN) {
#pragma unroll 1
        for (int u = 0; u < 12; u++) {
          if (u == 2 || u == 8) mbar_wait(bar_ring + 8 + (u & 8), 0);
          if (u >= FPACE) mbar_wait(bar_box + (u - FPACE) * 8, 0);
          const uint32_t dst = base + unit_of(u < 4 ? FT_G : (u < 8 ? FT_U : FT_D), u & 3);
          if (elect_one()) {
            mbar_expect_tx(bar_box + u * 8, UNIT);
            if (u < 8) tma2d(dst, u < 4 ? &maps.wg : &maps.wu, b * 32, (u & 3) * 256, bar_box + u * 8);
            else tma3d(dst, &maps.wd, 0, b * 32, (u - 8) * 4, bar_box + u * 8);
          }
        }
      }
    } else if (warp == 9) {
      const uint32_t target = 8 * (epoch + 1);
#pragma unroll 1
      for (int i = 0; i < 16; i++) {
        if (i == HDX) mbar_wait(bar_mod, 0);
        if (i == NRS) {
          wait_counter(&g_cnt_h[rb * 32], target);
          PROF(1, lane == 0, 26);
          fence_async();
        }
        mbar_wait(xempty + (i & 3) * 8, ((i >> 2) & 1) ^ 1);
        if (elect_one()) {
          mbar_expect_tx(xfull + (i & 3) * 8, UNIT);
          if (i < NRS) tma2d(base + (i & 3) * GST_BYTES, &maps.x, ((2 * cj + i) & 15) * 64, rb * 128, xfull + (i & 3) * 8);
          else bulk_load_stream(base + (i & 3) * GST_BYTES, g_act + (uint32_t)(rb * 80 + ((2 * cj + i) & 15)) * UNIT, UNIT, xfull + (i & 3) * 8);
        }
      }
      prefetch_map(&maps.wo);
#pragma unroll 1
      for (int t = 0; t < 4; t++) {
#pragma unroll 1
        for (int w = 0; w < 2; w++) {
          mbar_wait(bar_ofull + w * 8, t & 1);
          uint8_t* dst = g_act + (uint32_t)(rb * 80 + 16 + (cj * 4 + t) * 2) * UNIT + w * 8192;
          if (elect_one()) {
            bulk_store(dst, base + unit_of(QT, 2 * t) + w * 8192, 8192);
            bulk_store(dst + UNIT, base + unit_of(QT, 2 * t + 1) + w * 8192, 8192);
            asm volatile("cp.async.bulk.commit_group;" ::: "memory");
          }
        }
        if (elect_one()) {
          asm volatile("cp.async.bulk.wait_group.read 0;" ::: "memory");
          mbar_arrive(bar_ofree + t * 8);
          asm volatile("cp.async.bulk.wait_group 0;" ::: "memory");
          fence_async();
          red_release(&g_cnt_o[((rb * 4 + t) * 2 + (cj >> 2)) * 32], 2);
        }
        if (t & 1) {
          wait_counter(&g_cnt_o[(rb * 8 + 2 * t - 2 + (cj & 1)) * 32], target);
          wait_counter(&g_cnt_o[(rb * 8 + 2 * t + (cj & 1)) * 32], target);
        }
      }
      wait_counter(&g_cnt_o[(rb * 8 + 7 - (cj & 1)) * 32], target);
      fence_async();
      if (elect_one()) {
        mbar_arrive(bar_cnt);
        PROF(2, true, 27);
        mbar_expect_tx(bar_xres, 32768);
      }
#pragma unroll 1
      for (int u = 0; u < 2; u++) {
        mbar_wait(bar_res, u);
        if (elect_one()) tma2d(base + OFF_RES + u * UNIT, &maps.x, cj * 128 + u * 64, rb * 128, bar_xres);
      }
    } else {
      const int t2 = tid - 320;
      if (t2 == 0) {
        mbar_wait(bar_hpub, 0);
        PROF(1, true, 24);
        red_release(&g_cnt_h[rb * 32], 1);
        PROF(1, true, 25);
        prefetch_map(&maps.wg); prefetch_map(&maps.wu); prefetch_map(&maps.wd); prefetch_map(&maps.out);
      }
      __syncwarp();
      if (b < NFFN) {
        mbar_wait(bar_go2, 0);
        const __nv_bfloat16* pg = ((b & 1) ? P.w_up : P.w_gate) + (b >> 1) * 64 + (size_t)t2 * FF;
        const __nv_bfloat16* pd = P.w_down + (size_t)b * 32768 + t2 * 64;
        PROF(2, t2 == 0, 13);
#pragma unroll 1
        for (int i = 0; i < WN; i += WB) {
          uint32_t v[WB];
#pragma unroll
          for (int u = 0; u < WB; u++)
            asm volatile("ld.global.cg.L2::128B.u32 %0, [%1];" : "=r"(v[u]) : "l"(i < 16 ? pg + (size_t)(i + u) * 64 * FF : pd + (i + u - 16) * 4096));
#pragma unroll
          for (int u = 1; u < WB; u++) v[0] ^= v[u];
          sts1(par + PAR_SINK + t2 * 4, v[0]);
        }
        PROF(2, t2 == 0, 14);
      }
      const uint32_t tag = epoch % 3 + 1;
      mbar_wait(bar_go, 0);
      if (warp == 10) {
        const uint32_t* src = g_mod + 2 * DM + cj * 128 + lane * 4;
        const uint2 wr = *reinterpret_cast<const uint2*>(P.w_r + cj * 128 + lane * 4);
        uint4 vga, vsb, vcb, vgb;
        uint32_t n = 0;
        do {
          vga = ld_relaxed4(src); vsb = ld_relaxed4(src + DM); vcb = ld_relaxed4(src + 2 * DM); vgb = ld_relaxed4(src + 3 * DM);
          watchdog(n);
        } while (!(tag_ok(vga, tag) && tag_ok(vsb, tag) && tag_ok(vcb, tag) && tag_ok(vgb, tag)));
        const float c0 = rbf(1.f + bf_hi(vcb.x)), c1 = rbf(1.f + bf_hi(vcb.y)), c2 = rbf(1.f + bf_hi(vcb.z)), c3 = rbf(1.f + bf_hi(vcb.w));
        const float a0 = c0 * bf_lo(wr.x), a1 = c1 * bf_hi(wr.x), a2 = c2 * bf_lo(wr.y), a3 = c3 * bf_hi(wr.y);
        const uint32_t h0 = pack_bf(a0, a1), h1 = pack_bf(a2, a3);
        const uint32_t t1 = par + PAR_T1 + (lane >> 2) * 64 + (lane & 1) * 32 + (lane & 2) * 2;
        sts1(t1, h0); sts1(t1 + 8, pack_bf(a0 - bf_lo(h0), a1 - bf_hi(h0)));
        sts1(t1 + 16, h1); sts1(t1 + 24, pack_bf(a2 - bf_lo(h1), a3 - bf_hi(h1)));
        sts4(par + PAR_T2 + lane * 32, make_uint4(pack_bf(c0, c1), __byte_perm(vsb.x, vsb.y, 0x7632), __byte_perm(vgb.x, vgb.y, 0x7632), __byte_perm(vga.x, vga.y, 0x7632)));
        sts4(par + PAR_T2 + lane * 32 + 16, make_uint4(pack_bf(c2, c3), __byte_perm(vsb.z, vsb.w, 0x7632), __byte_perm(vgb.z, vgb.w, 0x7632), __byte_perm(vga.z, vga.w, 0x7632)));
      } else if (lane < 4) {
        const uint4 g = poll4(lane < 2 ? g_mod + 5 * DM + b * 8 + lane * 4 : g_mod + 16 - lane * 4, tag);
        if (lane < 2) sts4(par + PAR_CONST + 16 + lane * 16, g);
        else sts2(par + PAR_CONST + (lane - 2) * 8, __float_as_uint(untag_sum(g.x, g.y) + untag_sum(g.z, g.w)), epoch);
      }
      __syncwarp();
#pragma unroll 4
      for (int q = XR; q < XE; q++) st_b128(g_xch + ((size_t)b * 8 * 256 + q * 64 + t2) * 4, (epoch & 1) << 16, 0, 0, 0);
      for (int q = 0; q < 2; q++) st_relaxed4(g_stats + ((size_t)cj * SEQ + rb * 128 + q * 64 + t2) * 4, 0, 0, 0, 0);
      if (b < NFFN)
        for (int q = 0; q < 4; q++) st_relaxed4(g_ypart + ((size_t)(q * 32 + (t2 >> 1)) * NFFN + b) * 8 + (t2 & 1) * 4, 0, 0, 0, 0);
      st_relaxed4(g_row + rb * 2 * DM + (t2 >> 5) * DM + cj * 128 + (t2 & 31) * 4, 0, 0, 0, 0);
      if (t2 < 16) st_relaxed2(g_cand + (cj * 16 + t2) * 32 + rb * 2, 0, 0);
      __threadfence();
      mbar_arrive(bar_par);
    }
    __syncwarp();
    cluster_arrive();
    {
      const uint32_t tag = epoch % 3 + 1, t3 = tid - 256;
      mbar_wait(bar_win, 0);
      const uint2 win = lds2(par + PAR_CONST + 56);
      const uint32_t* fsrc = g_row + (win.y >> 7) * 2 * DM + (b >> 1) * 16 + (t3 & 3) * 4 + (b & 1) * 2;
      const uint32_t* ysrc = g_ypart + ((size_t)b * NFFN + min(t3, NFFN - 1)) * 8;
      uint2 fh = ld_pair(fsrc), fx = ld_pair(fsrc + DM);
      uint4 ya = ld_relaxed4(ysrc), yb = ld_relaxed4(ysrc + 4);
      const float rwin = __uint_as_float(((int)win.x < 0 ? win.x & 0x7fffffffu : ~win.x) & ~3u);
      const float rs = rbf(rcp(1.f + __expf(-rbf(rwin))));
      uint32_t n = 0;
      while (fh.y != tag || fx.y != tag) { fh = ld_pair(fsrc); fx = ld_pair(fsrc + DM); watchdog(n); }
      while (!(tag_ok(ya, tag) && tag_ok(yb, tag))) { ya = ld_relaxed4(ysrc); yb = ld_relaxed4(ysrc + 4); watchdog(n); }
      __syncwarp();
      PROF(8, t3 == 0, 5);
      const uint32_t msk = t3 < NFFN ? ~3u : 0u;
      float y[8] = {__uint_as_float(ya.x & msk), __uint_as_float(ya.y & msk), __uint_as_float(ya.z & msk), __uint_as_float(ya.w & msk),
                    __uint_as_float(yb.x & msk), __uint_as_float(yb.y & msk), __uint_as_float(yb.z & msk), __uint_as_float(yb.w & msk)};
#pragma unroll
      for (int h = 4; h > 0; h >>= 1) {
        const bool up = lane & (h * 4);
#pragma unroll
        for (int e = 0; e < h; e++) y[e] = (up ? y[e + h] : y[e]) + __shfl_xor_sync(0xffffffffu, up ? y[e] : y[e + h], h * 4);
      }
      y[0] += __shfl_xor_sync(0xffffffffu, y[0], 1);
      y[0] += __shfl_xor_sync(0xffffffffu, y[0], 2);
      if ((lane & 3) == 0) sts1(par + PAR_RED + 64 + t3, __float_as_uint(y[0]));
      bar_sync(4, 128);
      if (t3 < 4) {
        float y0 = 0.f, y1 = 0.f;
#pragma unroll
        for (int w4 = 0; w4 < 4; w4++) {
          const uint2 v = lds2(par + PAR_RED + 64 + w4 * 32 + t3 * 8);
          y0 += __uint_as_float(v.x); y1 += __uint_as_float(v.y);
        }
        const uint2 gv = lds2(par + PAR_CONST + 16 + t3 * 8);
        const uint32_t upd = hmul2(pack_bf(y0, y1), pack_bf(rs, rs));
        *reinterpret_cast<uint32_t*>(P.out + (size_t)win.y * DM + b * 8 + t3 * 2) =
            hadd2(fx.x, hmul2(__byte_perm(gv.x, gv.y, 0x7632), hadd2(fh.x, upd)));
        if (b == 0 && t3 == 0) st_relaxed(&g_epoch, epoch + 1);
      }
      PROF(31, t3 == 0, 36);
    }
    cluster_wait();
  } else {
    const int wg = warp >> 2;

    uint32_t tag;
    {
      uint32_t* const pmod = g_modp + rank * 2 * DM + (b >> 1) * 32 + lane;
      uint32_t* const pln = g_ln1 + (rb * 128 + cj * 16 + warp) * 4;
      const uint32_t cv = ldg_nc1(P.c + rank * 512 + tid * 2);
      const uint32_t epoch = ld_relaxed(&g_epoch);
      if (warp == 0) st_relaxed(pmod, 0);
      if (lane == 0) { st_relaxed2(pln, 0, 0); st_relaxed2(pln + 32, 0, 0); }
      asm volatile("setmaxnreg.inc.sync.aligned.u32 232;");
      sts1(par + tid * 4, pack_bf(silu_f(bf_lo(cv)), silu_f(bf_hi(cv))));
      bar_sync(1, 320);
      tag = epoch % 3 + 1;
#pragma unroll
      for (int part = 0; part < 3; part++) {
        if (part != 1) {
          const uint32_t xa = base + (2 + part / 2) * GST_BYTES + warp * 2048 + lane * 16;
          mbar_wait(bar_hx + part * 4, 0);
          float s0 = 0.f, s1 = 0.f, q0 = 0.f, q1 = 0.f;
#pragma unroll
          for (int q = 0; q < 4; q++) {
            const uint4 xv = lds4(xa + q * 512);
            const uint32_t u[4] = {xv.x, xv.y, xv.z, xv.w};
#pragma unroll
            for (int e = 0; e < 4; e++) { const float lo = bf_lo(u[e]), hi = bf_hi(u[e]); s0 += lo; s1 += hi; q0 += lo * lo; q1 += hi * hi; }
          }
          s0 += s1; q0 += q1;
#pragma unroll
          for (int o = 16; o > 0; o >>= 1) { s0 += __shfl_xor_sync(0xffffffffu, s0, o); q0 += __shfl_xor_sync(0xffffffffu, q0, o); }
          const float mean = s0 * (1.f / DM);
          float mb, sd;
          ln_scalars(mean, fmaxf(q0 * (1.f / DM) - mean * mean, 0.f), mb, sd);
          if (lane == 0) st_relaxed2(pln + part * 16, __float_as_uint(mb) | tag, __float_as_uint(sd) | tag);
          PROF(1, tid == 0 && part == 2, 4);
        } else {
          float acc[8];
#pragma unroll
          for (int e = 0; e < 8; e++) acc[e] = 0.f;
          const uint32_t wa = stage + (tid >> 2) * 64 + (((tid ^ (tid >> 3)) & 3) << 4), sa = par + (tid >> 3) * 4, sh = (tid & 4) ? 0x3244 : 0x1044;
          mbar_wait(bar_hw, 0);
#pragma unroll
          for (int p = 0; p < 8; p++) {
            const uint4 w = lds4(wa + p * 4096);
            const float s = __uint_as_float(__byte_perm(lds1(sa + p * 128), 0, sh));
            acc[0] += s * bf_lo(w.x); acc[1] += s * bf_hi(w.x); acc[2] += s * bf_lo(w.y); acc[3] += s * bf_hi(w.y);
            acc[4] += s * bf_lo(w.z); acc[5] += s * bf_hi(w.z); acc[6] += s * bf_lo(w.w); acc[7] += s * bf_hi(w.w);
          }
#pragma unroll
          for (int e = 0; e < 4; e++) {
            const bool up = lane & 16;
            acc[e] = (up ? acc[e + 4] : acc[e]) + __shfl_xor_sync(0xffffffffu, up ? acc[e] : acc[e + 4], 16);
          }
#pragma unroll
          for (int e = 0; e < 2; e++) {
            const bool up = lane & 8;
            acc[e] = (up ? acc[e + 2] : acc[e]) + __shfl_xor_sync(0xffffffffu, up ? acc[e] : acc[e + 2], 8);
          }
          {
            const bool up = lane & 4;
            acc[0] = (up ? acc[1] : acc[0]) + __shfl_xor_sync(0xffffffffu, up ? acc[0] : acc[1], 4);
          }
          sts1(par + 1024 + warp * 128 + ((lane & 3) * 8 + (lane >> 2)) * 4, __float_as_uint(acc[0]));
          bar_sync(1, 256);
          if (warp == 0) {
            float s = 0.f;
#pragma unroll
            for (int w8 = 0; w8 < 8; w8++) s += __uint_as_float(lds1(par + 1024 + w8 * 128 + lane * 4));
            st_relaxed(pmod, (__float_as_uint(s) & ~3u) | tag);
          }
          PROF(1, tid == 0, 3);
        }
      }
      {
        uint2 s0 = ld_relaxed2(g_ln1 + (rb * 128 + (tid & 127)) * 4);
        uint4 v[4];
#pragma unroll
        for (int q = 0; q < 4; q++) v[q] = ld_relaxed4(g_modp + q * DM + tid * 4);
        {
          uint32_t n = 0;
          while (!(tag_ok(v[0], tag) && tag_ok(v[1], tag) && tag_ok(v[2], tag) && tag_ok(v[3], tag))) {
#pragma unroll
            for (int q = 0; q < 4; q++)
              if (!tag_ok(v[q], tag)) v[q] = ld_relaxed4(g_modp + q * DM + tid * 4);
            if (((s0.x ^ tag) | (s0.y ^ tag)) & 3u) s0 = ld_relaxed2(g_ln1 + (rb * 128 + (tid & 127)) * 4);
            watchdog(n);
          }
        }
        const uint32_t d = stage + (tid >> 2) * 64 + (tid & 1) * 32 + (tid & 2) * 2;
        sts1(d, pack_bf(1.f + rbf(untag_sum(v[1].x, v[3].x)), 1.f + rbf(untag_sum(v[1].y, v[3].y))));
        sts1(d + 16, pack_bf(1.f + rbf(untag_sum(v[1].z, v[3].z)), 1.f + rbf(untag_sum(v[1].w, v[3].w))));
        sts1(d + 8, pack_bf(untag_sum(v[0].x, v[2].x), untag_sum(v[0].y, v[2].y)));
        sts1(d + 24, pack_bf(untag_sum(v[0].z, v[2].z), untag_sum(v[0].w, v[2].w)));
        if (wg == 0) {
          uint32_t n = 0;
          while (((s0.x ^ tag) | (s0.y ^ tag)) & 3u) { s0 = ld_relaxed2(g_ln1 + (rb * 128 + tid) * 4); watchdog(n); }
          uint32_t ih, il;
          split_inv(bf_hi(s0.y), ih, il);
          sts4(stage + 4096 + tid * 16, make_uint4(__byte_perm(s0.x, 0, 0x3232), ih, il, 0));
        }
        mbar_arrive(bar_mod);
      }
      cluster_wait();
      if (wg == 1) bar_arrive(2, 256);
      mbar_wait(bar_mod, 0);
      PROF(1, tid == 0, 2);
    }

    float f0 = 0.f, f1 = 0.f;
    const uint32_t rempty = lane < 2 ? mapa(bempty, lane & 1) : 0;
    constexpr uint32_t GE = NSLOT * 8 + 32;
    float o[64], s[64];
#pragma unroll 1
    for (int ps = 0; ps < 3; ps++) {
      {
        const uint32_t xt = ps == 1 ? XT1 : XT2, wt = ps == 1 ? WT1 : WT2;
        const int nst = ps == 2 ? 28 : 14;
        if (ps == 0) {
          float ga[64], gb[64];
#pragma unroll
          for (int i = 0; i < 64; i++) { ga[i] = 0.f; gb[i] = 0.f; }
          uint32_t a[2][16];
          const uint32_t l = fresh_lane();
          const uint4 r0 = lds4(stage + 4096 + (warp * 16 + (l >> 2)) * 16), r1 = lds4(stage + 4096 + 128 + (warp * 16 + (l >> 2)) * 16);
          auto transform = [&](int i, uint32_t (&f)[16], uint32_t z) {
            const uint32_t ad = base + (i & 3) * GST_BYTES + wg * 8192 + frag_offset(warp) + z;
            mbar_wait(xfull + (i & 3) * 8, i >> 2);
#pragma unroll
            for (int kk = 0; kk < 4; kk++) ldmatrix4(ad ^ (kk * 32), f[4 * kk], f[4 * kk + 1], f[4 * kk + 2], f[4 * kk + 3]);
#pragma unroll
            for (int kk = 0; kk < 4; kk++) {
              const uint4 m = lds4(stage + (l & 3) * 16 + ((2 * cj + i) & 15) * 256 + kk * 64);
              f[4 * kk] = ln_mod(f[4 * kk], r0.x, r0.y, r0.z, m.x, m.z);
              f[4 * kk + 1] = ln_mod(f[4 * kk + 1], r1.x, r1.y, r1.z, m.x, m.z);
              f[4 * kk + 2] = ln_mod(f[4 * kk + 2], r0.x, r0.y, r0.z, m.y, m.w);
              f[4 * kk + 3] = ln_mod(f[4 * kk + 3], r1.x, r1.y, r1.z, m.y, m.w);
            }
            keep(f);
            mbar_arrive_pred(xempty + (i & 3) * 8, l == 0);
          };
          auto publish = [&](int u, uint32_t (&f)[16]) {
            const uint32_t sc = stage + 8192 + wg * 8192;
#pragma unroll
            for (int kk = 0; kk < 4; kk++) stmatrix4((sc + frag_offset(warp)) ^ (kk * 32), f[4 * kk], f[4 * kk + 1], f[4 * kk + 2], f[4 * kk + 3]);
            __syncwarp();
            const uint32_t src = sc + (warp & 3) * 2048 + l * 16;
            uint8_t* dst = g_act + (uint32_t)(rb * 80 + cj * 2 + u) * UNIT + warp * 2048 + l * 16;
#pragma unroll
            for (int p4 = 0; p4 < 4; p4++) stg4(dst + p4 * 512, lds4(src + p4 * 512));
            __syncwarp();
            if (u == 1) mbar_arrive_pred(bar_hpub, l == 0);
          };
          auto multiply = [&](int i, uint32_t (&f)[16]) {
            mbar_wait(gfull + (i & 3) * 8, i >> 2);
            const uint64_t db = make_desc(base + (i & 3) * GST_BYTES + UNIT, 8192, 1024);
            wg_fence();
#pragma unroll
            for (int kk = 0; kk < 4; kk++) mma256_rs(ga, gb, f[4 * kk], f[4 * kk + 1], f[4 * kk + 2], f[4 * kk + 3], db + kk * 128);
            wg_commit();
          };
          transform(0, a[0], 0); publish(0, a[0]); transform(1, a[1], 0); multiply(0, a[0]); publish(1, a[1]);
#pragma unroll
          for (int i = 1; i < NRS; i++) {
            if (i >= 2) {
              uint32_t z = r0.w;
#pragma unroll
              for (int k = 0; k < 16; k += 2) asm volatile("lop3.b32 %0, %1, %2, %0, 0xA8;" : "+r"(z) : "r"(a[i & 1][k]), "r"(a[i & 1][k + 1]));
              transform(i, a[i & 1], z);
            }
            multiply(i, a[i & 1]);
            wg_wait<1>();
            mbar_arrive_cl(rempty, GE + ((i + 3) & 3) * 8);
          }
          mbar_arrive_pred(bar_pread, l == 0);
#pragma unroll 1
          for (int i = NRS; i < 14; i++) {
            mbar_wait(xfull + (i & 3) * 8, (i >> 2) & 1);
            mbar_wait(gfull + (i & 3) * 8, (i >> 2) & 1);
            const uint32_t xa = base + (i & 3) * GST_BYTES;
            const uint64_t da = make_desc(xa + wg * 8192, 16, 1024), db = make_desc(xa + UNIT, 8192, 1024);
            if (i == 13) bar_sync(2 + wg, 256);
            wg_fence();
#pragma unroll
            for (int kk = 0; kk < 4; kk++) mma256_ss(ga, gb, da + kk * 2, db + kk * 128, 1);
            wg_commit();
            if (i == 13) bar_arrive(3 - wg, 256);
            wg_wait<1>();
            uint32_t z = r0.w;
#pragma unroll
            for (int k = 0; k < 16; k += 2) asm volatile("lop3.b32 %0, %1, %2, %0, 0xA8;" : "+r"(z) : "r"(a[1][k]), "r"(a[1][k + 1]));
            mbar_arrive_cl(rempty, GE + ((i + 3) & 3) * 8 + z);
            mbar_arrive_pred(xempty + ((i + 3) & 3) * 8, l == 0 && i != NRS);
          }
          mbar_wait(xfull + 16, 1);
          mbar_wait(xfull + 24, 1);
          wg_wait<0>();
          keep(ga); keep(gb);
#pragma unroll
          for (int i = 0; i < 64; i++) {
            asm volatile("mov.b32 %0, %1;" : "=f"(s[i]) : "f"(ga[i]));
            asm volatile("mov.b32 %0, %1;" : "=f"(o[i]) : "f"(gb[i]));
          }
        } else {
          float ga[64], gb[64];
#pragma unroll
          for (int i = 0; i < 64; i++) {
            asm volatile("mov.b32 %0, %1;" : "=f"(ga[i]) : "f"(s[i]));
            asm volatile("mov.b32 %0, %1;" : "=f"(gb[i]) : "f"(o[i]));
          }
#pragma unroll 1
          for (int i = 0; i < nst; i++) {
            mbar_wait(gfull + (i & 3) * 8, (i >> 2) & 1);
            const uint64_t da = make_desc(base + unit_of(xt, i & 3) + wg * 8192, 16, 1024), db = make_desc(base + unit_of(wt, i & 3), 8192, 1024);
            if (i == nst - 1) bar_sync(2 + wg, 256);
            wg_fence();
#pragma unroll
            for (int kk = 0; kk < 4; kk++) mma256_ss(ga, gb, da + kk * 2, db + kk * 128, kk ? 1 : i);
            wg_commit();
            if (i == nst - 1) bar_arrive(3 - wg, 256);
            wg_wait<1>();
            mbar_arrive_cl(rempty, GE + ((i + 3) & 3) * 8, i != 0);
            PROF(4, tid == 0 && (i & 3) == 0, 40 + (ps - 1) * 4 + i / 4);
          }
          wg_wait<0>();
          keep(ga); keep(gb);
#pragma unroll
          for (int i = 0; i < 64; i++) {
            asm volatile("mov.b32 %0, %1;" : "=f"(s[i]) : "f"(ga[i]));
            asm volatile("mov.b32 %0, %1;" : "=f"(o[i]) : "f"(gb[i]));
          }
        }
        mbar_arrive_cl(rempty, GE + (ps == 2 ? 24 : 8));
        if (ps == 2) break;
      }
      const uint32_t qw = base + wg * 8192, qt = QT >> (16 * ps), at = ps ? AT1 : AT0;
      {
        const uint32_t wt = ps ? WT1 : WT0;
        const uint64_t da0 = make_desc(qw + unit_of(qt, 2), 16, 1024), da1 = make_desc(qw + unit_of(qt, 3), 16, 1024);
        const uint64_t db0 = make_desc(base + unit_of(wt, 2), 8192, 1024), db1 = make_desc(base + unit_of(wt, 3), 8192, 1024);
        mbar_wait(gfull + 16, 1);
        mbar_wait(gfull + 24, 1);
        bar_sync(2 + wg, 256);
        wg_fence();
#pragma unroll
        for (int kk = 0; kk < 8; kk++) mma_ss<1>(s, (kk < 4 ? da0 : da1) + (kk & 3) * 2, (kk < 4 ? db0 : db1) + (kk & 3) * 128, 1);
        wg_commit();
        bar_arrive(3 - wg, 256);
        mbar_wait(ps == 0 ? bar_pread : bar_ofree + 8, 0);
        mbar_wait(bfull, 0);
        wg_wait<0>();
        keep(s);
        PROF(2, tid == 0, 8 + ps * 8);
        store_chunk<0>(s, qw + unit_of(qt, 0) + frag_offset(warp));
        store_chunk<1>(s, qw + unit_of(qt, 1) + frag_offset(warp));
        fence_async_smem();
        bar_sync(2 + wg, 256);
        wg_fence();
        issue_qk(s, qw + unit_of(qt, 0), qw + unit_of(qt, 1), base + unit_of(at, 0));
        wg_commit();
#pragma unroll
        for (int kk = 0; kk < 8; kk++) mma_ss<1>(o, (kk < 4 ? da0 : da1) + (kk & 3) * 2, (kk < 4 ? db0 : db1) + UNIT / 16 + (kk & 3) * 128, 1);
        wg_commit();
        bar_arrive(3 - wg, 256);
        wg_wait<1>();
        keep(s);
        mbar_arrive_cl(rempty, 0);
      }
      PROF(4, tid == 0 && ps == 1, 61);
      float l0 = 0.25f, l1 = 0.25f;
      auto step = [&](auto odd_c, const int j, uint32_t (&pw)[32], uint32_t (&pr)[32]) {
        constexpr bool ODD = decltype(odd_c)::value;
        const bool first = !ODD && (j & 2) == 0, last = ODD && j == 7;
        const uint32_t ph = (j >> 1) & 1;
        float i0, i1, a0, a1;
        if (first) { i0 = inv_quad_sum(l0); i1 = inv_quad_sum(l1); l0 = 0.f; l1 = 0.f; }
        bool redo = !ODD && (j | ps) == 0, again = false;
        while (true) {
          if (redo) {
            float m0 = fmaxf(s[0], s[1]), m1 = fmaxf(s[2], s[3]);
#pragma unroll
            for (int i = 1; i < 16; i++) { m0 = fmaxf(m0, fmaxf(s[4 * i], s[4 * i + 1])); m1 = fmaxf(m1, fmaxf(s[4 * i + 2], s[4 * i + 3])); }
            m0 = fmaxf(m0, __shfl_xor_sync(0xffffffffu, m0, 1)); m1 = fmaxf(m1, __shfl_xor_sync(0xffffffffu, m1, 1));
            m0 = fmaxf(m0, __shfl_xor_sync(0xffffffffu, m0, 2)); m1 = fmaxf(m1, __shfl_xor_sync(0xffffffffu, m1, 2));
            m0 *= SCL2; m1 *= SCL2;
            if (!first) {
              m0 = fmaxf(m0, f0); m1 = fmaxf(m1, f1);
              const float c0 = ex2(f0 - m0), c1 = ex2(f1 - m1);
              l0 *= c0; l1 *= c1;
              wg_wait<0>();
              keep(o);
#pragma unroll
              for (int i = 0; i < 16; i++) { o[4 * i] *= c0; o[4 * i + 1] *= c0; o[4 * i + 2] *= c1; o[4 * i + 3] *= c1; }
            }
            f0 = m0; f1 = m1;
          }
          float b0 = 0.f, b1 = 0.f;
          a0 = 0.f; a1 = 0.f;
#pragma unroll
          for (int i = 0; i < 16; i++) {
            const float e0 = ex2(fmaf(s[4 * i], SCL2, -f0)), e1 = ex2(fmaf(s[4 * i + 1], SCL2, -f0));
            const float e2 = ex2(fmaf(s[4 * i + 2], SCL2, -f1)), e3 = ex2(fmaf(s[4 * i + 3], SCL2, -f1));
            a0 += e0; b0 += e1; a1 += e2; b1 += e3;
            pw[2 * i] = pack_bf(e0, e1); pw[2 * i + 1] = pack_bf(e2, e3);
            if (i == VREL) {
#pragma unroll
              for (int k = 0; k < 2 * VREL + 2; k++) asm volatile("" : "+r"(pw[k])::"memory");
              mbar_wait(bfull + (ODD ? 24 : 8), ph);
              wg_wait<0>();
              mbar_arrive_cl(rempty, ODD ? 16 : (j ? 0 : GE + 16), !again);
              if (!ODD) mbar_arrive_cl(rempty, GE + 24, !again && j == 0);
#pragma unroll
              for (int k = 4 * VREL + 4; k < 64; k++) asm volatile("" : "+f"(s[k])::"memory");
            }
          }
          a0 += b0; a1 += b1;
          if (redo) break;
          redo = __any_sync(0xffffffffu, !(a0 + a1 < 0x1p70f));
          if (first) {
            uint32_t m0 = __ballot_sync(0xffffffffu, a0 > 0x1p-50f), m1 = __ballot_sync(0xffffffffu, a1 > 0x1p-50f);
            m0 |= m0 >> 1; m1 |= m1 >> 1; m0 |= m0 >> 2; m1 |= m1 >> 2;
            redo = redo || (m0 & m1 & 0x11111111u) != 0x11111111u;
          }
          if (!redo) break;
          again = true;
        }
        l0 += a0; l1 += a1;
        keep(pw);
        keep(o);
        const uint32_t qo = qt >> (j ? 0 : 8);
        if (first) store_chunk<0>(o, i0, i1, qw + unit_of(qo, 0) + frag_offset(warp));
        keep(o);
        bar_sync(2 + wg, 256);
        if (!last) {
          const uint32_t qn = qt >> (j >= 3 ? 8 : 0);
          wg_fence();
          issue_qk(s, qw + unit_of(qn, 0), qw + unit_of(qn, 1), base + unit_of(at, ODD ? 3 : 1));
          wg_commit();
          mbar_wait(bfull + (ODD ? 0 : 16), ODD ? ph ^ 1 : ph);
        }
        if (first) { store_chunk<1>(o, i0, i1, qw + unit_of(qo, 1) + frag_offset(warp)); keep(o); }
        wg_fence();
        issue_pv(o, pw, base + unit_of(at, ODD ? (last ? 3 : 0) : 2), !first);
        wg_commit();
        bar_arrive(3 - wg, 256);
        if (first) { fence_async_smem(); mbar_arrive_pred(bar_ofull + wg * 8, j); PROF(2, tid == 0 && j, 9 + ps * 8); }
        wg_wait<1>();
        keep(s);
        mbar_arrive_cl(rempty, ODD ? 24 : 8, !last);
        PROF(4, tid == 0 && ps == 1, 51 + j);
      };
      uint32_t pa[32], pb[32];
#pragma unroll 1
      for (int j = 0; j < 8; j += 2) {
        step(std::false_type{}, j, pa, pb);
        step(std::true_type{}, j + 1, pb, pa);
      }
      {
        const float i0 = inv_quad_sum(l0), i1 = inv_quad_sum(l1);
        wg_wait<0>();
        keep(o);
        mbar_arrive_cl(rempty, 24);
        store_chunk<0>(o, i0, i1, qw + unit_of(qt, 2) + frag_offset(warp));
        store_chunk<1>(o, i0, i1, qw + unit_of(qt, 3) + frag_offset(warp));
        fence_async_smem();
        mbar_arrive(bar_ofull + wg * 8);
      }
      PROF(2, tid == 0, 10 + ps * 8);
    }

    const int ln = fresh_lane(), g = ln >> 2, tq = ln & 3, ct = warp * 32 + ln;
    const bool lane0 = ln == 0;
    const int lrow0 = warp * 16 + g;
    const int grow0 = rb * 128 + lrow0;
    const uint32_t res = base + OFF_RES, trow = res + wg * 8192 + frag_offset(warp);
    uint32_t xr[32];
    {
      const uint64_t da = make_desc(base + wg * 8192, 16, 1024), db = make_desc(base, 8192, 1024);
      constexpr int U = UNIT / 16;
#define HALF_STAGE(acc, xu, wu) _Pragma("unroll") for (int kk = 0; kk < 4; kk++) mma_ss<1>(acc, da + (xu) * U + kk * 2, db + (wu) * U + kk * 128, 1)
      PROF(10, ct == PT, 19); STAMP(0);
      cluster_arrive();
      mbar_wait(gfull, 1);
      mbar_wait(gfull + 8, 1);
      bar_sync(2 + wg, 256);
      wg_fence();
      HALF_STAGE(o, 6, 8);
      HALF_STAGE(o, 9, 11);
      wg_commit();
      STAMP(16);
      mbar_wait(gfull + 16, 1);
      STAMP(17);
      wg_fence();
      HALF_STAGE(o, 12, 1);
      wg_commit();
      bar_arrive(3 - wg, 256);
      mbar_wait(bar_par, 0);
      uint32_t* xo = g_xch + ((size_t)b * 8 * 256 + ct) * 4;
      const uint32_t* xi = g_xch + ((size_t)(b ^ 2) * 8 * 256 + ct) * 4;
      const uint32_t par1 = (~lds1(par + PAR_CONST + 4) & 1) << 16;
      wg_wait<0>();
      keep(o);
      mbar_arrive_pred(bar_ring, lane0);
      PROF(8, ct == PT, 20); STAMP(1);
#define SEND(i) st_b128(xo + (i) * 1024, (pack_bf(o[8 * (i)], o[8 * (i) + 1]) & ~0x10000u) | par1, pack_bf(o[8 * (i) + 2], o[8 * (i) + 3]), \
                        pack_bf(o[8 * (i) + 4], o[8 * (i) + 5]), pack_bf(o[8 * (i) + 6], o[8 * (i) + 7]))
#pragma unroll
      for (int i = 0; i < NS1; i++) SEND(i);
      PROF(8, ct == PT, 21); STAMP(2);
      bar_sync(2 + wg, 256);
      wg_fence();
      HALF_STAGE(s, 6, 7);
      HALF_STAGE(s, 9, 10);
      HALF_STAGE(s, 12, 0);
      wg_commit();
      bar_arrive(3 - wg, 256);
      STAMP(18);
      mbar_wait(gfull + 24, 1);
#pragma unroll
      for (int i = NS1; i < 8; i++) SEND(i);
      uint4 v[8];
#pragma unroll
      for (int i = 0; i < 4; i++) v[i] = ld_b128(xi + i * 1024);
      STAMP(19);
      mbar_wait(bar_rx, 0);
      wg_wait<0>();
      mbar_arrive_pred(bar_ring + 8, lane0);
      bar_sync(2 + wg, 256);
      STAMP(20);
#pragma unroll
      for (int i = 4; i < 8; i++) v[i] = ld_b128(xi + i * 1024);
      mbar_wait(bar_xres, 0);
      wg_fence();
      HALF_STAGE(s, 13, 2);
      HALF_STAGE(s, 8, 3);
      wg_commit();
      bar_arrive(3 - wg, 256);
      STAMP(21);
      wg_wait<0>();
      keep(s);
      mbar_arrive_pred(bar_ring + 16, lane0);
      PROF(10, ct == PT, 23); STAMP(4);
#pragma unroll
      for (int i = 0; i < 16; i += 2) ldmatrix4((trow ^ ((i & 7) << 4)) + (i >> 3) * 16384, xr[2 * i], xr[2 * i + 1], xr[2 * i + 2], xr[2 * i + 3]);
      {
        uint32_t n = 0;
        bool ok;
        do {
          ok = true;
#pragma unroll
          for (int i = 0; i < 8; i++)
            if ((v[i].x & 0x10000u) != par1) { v[i] = ld_b128(xi + i * 1024); ok = false; }
          watchdog(n);
        } while (!ok);
      }
      __syncwarp();
      PROF(8, ct == PT, 22); STAMP(3);
      float ds[4] = {0.f, 0.f, 0.f, 0.f}, dl[4] = {0.f, 0.f, 0.f, 0.f}, q0[4] = {0.f, 0.f, 0.f, 0.f}, q1[4] = {0.f, 0.f, 0.f, 0.f};
#pragma unroll
      for (int i = 0; i < 8; i++) {
        const uint32_t ga0 = lds1(par + PAR_T2 + i * 128 + tq * 16 + 12), ga1 = lds1(par + PAR_T2 + i * 128 + 64 + tq * 16 + 12);
        const uint4 bw = lds4(par + PAR_T1 + i * 64 + tq * 16);
        const uint32_t u0 = hfma2(ga0, hadd2(pack_bf(s[8 * i], s[8 * i + 1]), v[i].x & ~0x10000u), xr[4 * i]);
        const uint32_t u1 = hfma2(ga0, hadd2(pack_bf(s[8 * i + 2], s[8 * i + 3]), v[i].y), xr[4 * i + 1]);
        const uint32_t u2 = hfma2(ga1, hadd2(pack_bf(s[8 * i + 4], s[8 * i + 5]), v[i].z), xr[4 * i + 2]);
        const uint32_t u3 = hfma2(ga1, hadd2(pack_bf(s[8 * i + 6], s[8 * i + 7]), v[i].w), xr[4 * i + 3]);
        xr[4 * i] = u0; xr[4 * i + 1] = u1; xr[4 * i + 2] = u2; xr[4 * i + 3] = u3;
        mma16816(ds, u0, u1, u2, u3, (g & 1) ? bw.x : 0x3f803f80u, (g & 1) ? bw.y : 0x3f803f80u);
        mma16816(dl, u0, u1, u2, u3, bw.z, bw.w);
        mma16816(q0, u0, u1, u2, u3, u0, u2);
        mma16816(q1, u0, u1, u2, u3, u1, u3);
      }
      if (tq == (g >> 1)) {
        uint32_t* dst = g_stats + ((size_t)cj * SEQ + grow0) * 4;
        st_b128(dst, __float_as_uint(ds[0]), __float_as_uint((g & 1) ? q0[1] : q0[0]), __float_as_uint(ds[1] + dl[1]), tag);
        st_b128(dst + 32, __float_as_uint(ds[2]), __float_as_uint((g & 1) ? q1[3] : q1[2]), __float_as_uint(ds[3] + dl[3]), tag);
      }
    }
    PROF(8, ct == PT, 29); STAMP(5);
    uint32_t mm, ih, il;
    float rbest;
    {
      const uint32_t* sp = g_stats + ((size_t)(tq >> 1) * 4 * SEQ + grow0 + (tq & 1) * 8) * 4;
      uint4 v0 = ld_b128(sp), v1 = ld_b128(sp + SEQ * 4), v2 = ld_b128(sp + SEQ * 8), v3 = ld_b128(sp + SEQ * 12);
#pragma unroll
      for (int i = 0; i < 16; i += 2) stmatrix4((trow ^ ((i & 7) << 4)) + (i >> 3) * 16384, xr[2 * i], xr[2 * i + 1], xr[2 * i + 2], xr[2 * i + 3]);
      const uint4 cst = lds4(par + PAR_CONST);
      const float A1 = __uint_as_float(cst.x), A2 = __uint_as_float(cst.z);
      uint32_t n = 0;
      while (v0.w != tag || v1.w != tag || v2.w != tag || v3.w != tag) {
        if (v0.w != tag) v0 = ld_b128(sp);
        if (v1.w != tag) v1 = ld_b128(sp + SEQ * 4);
        if (v2.w != tag) v2 = ld_b128(sp + SEQ * 8);
        if (v3.w != tag) v3 = ld_b128(sp + SEQ * 12);
        watchdog(n);
      }
      __syncwarp();
      PROF(8, ct == PT, 30); STAMP(6);
      float su = (__uint_as_float(v0.x) + __uint_as_float(v1.x)) + (__uint_as_float(v2.x) + __uint_as_float(v3.x));
      float sq = (__uint_as_float(v0.y) + __uint_as_float(v1.y)) + (__uint_as_float(v2.y) + __uint_as_float(v3.y));
      float dt = (__uint_as_float(v0.z) + __uint_as_float(v1.z)) + (__uint_as_float(v2.z) + __uint_as_float(v3.z));
      su += __shfl_xor_sync(0xffffffffu, su, 2); sq += __shfl_xor_sync(0xffffffffu, sq, 2); dt += __shfl_xor_sync(0xffffffffu, dt, 2);
      const float m = su * (1.f / DM);
      float mb, sd;
      ln_scalars(m, fmaxf(sq * (1.f / DM) - m * m, 0.f), mb, sd);
      const float inv = rcp(sd);
      rbest = (dt - mb * A1) * inv + A2;
      mm = pack_bf(mb, mb);
      ih = pack_bf(inv, inv);
      const float lo = inv - bf_lo(ih);
      il = pack_bf(lo, lo);
    }
    int ibest;
    {
      const uint32_t bits = __float_as_uint(rbest) & ~3u, key = (int)bits < 0 ? ~bits : bits | 0x80000000u;
      const uint32_t kmax = __reduce_max_sync(0xffffffffu, key);
      const uint32_t row = __reduce_min_sync(0xffffffffu, key == kmax ? lrow0 + (tq & 1) * 8 : 255);
      if (lane0) sts2(par + PAR_RED + warp * 8, kmax, row);
      PROF(8, ct == PT, 38); STAMP(7);
      bar_sync(1, 256);
      const uint2 cv = lds2(par + PAR_RED + (ln & 7) * 8);
      const uint32_t k2 = __reduce_max_sync(0xffffffffu, cv.x);
      ibest = __reduce_min_sync(0xffffffffu, cv.x == k2 ? cv.y : 255);
      if (ct < 16) st_relaxed2(g_cand + (cj * 16 + ct) * 32 + rb * 2, (k2 & ~3u) | tag, ((rb * 128 + ibest) << 2) | tag);
    }
    PROF(8, ct == PT, 39); STAMP(8);
    if ((ibest >> 4) == warp) {
      const int src = (ibest & 7) * 4 + ((ibest >> 3) & 1), ch = g * 2;
      const uint32_t cm = __shfl_sync(0xffffffffu, mm, src), ch_ = __shfl_sync(0xffffffffu, ih, src), cl = __shfl_sync(0xffffffffu, il, src);
      const uint32_t xa = res + (ch >> 3) * 16384 + ibest * 128 + (((ch & 7) ^ (ibest & 7)) << 4) + tq * 4;
      const uint32_t x0 = lds1(xa), x1 = lds1(xa ^ 16);
      const uint2 p0 = lds2(par + PAR_T2 + ch * 64 + tq * 16), p1 = lds2(par + PAR_T2 + ch * 64 + 64 + tq * 16);
      uint32_t* dst = g_row + rb * 2 * DM + cj * 128 + ln * 4;
      st_pairs(dst, ln_mod(x0, cm, ch_, cl, p0.x, p0.y), ln_mod(x1, cm, ch_, cl, p1.x, p1.y), tag);
      st_pairs(dst + DM, x0, x1, tag);
      __syncwarp();
    }
    PROF(8, ct == PT, 37); STAMP(9);
    const uint32_t* inbox = g_cand + b * 32 + (ln & 15) * 2;
    uint2 cv = ld_relaxed2(inbox);
    uint32_t wf[128];
    const uint32_t frow = (ln & 7) + (ln >> 4) * 8;
    const uint32_t wfo = base + (warp & 1) * 8192 + frow * 64 + ((((ln >> 3) & 1) ^ ((frow >> 1) & 3)) << 4);
    if (b < NFFN) {
#pragma unroll
      for (int m = 0; m < 2; m++) {
        const uint32_t wfa = wfo + unit_of(m ? FT_U : FT_G, warp >> 1);
        mbar_wait(bar_box + (m * 4 + (warp >> 1)) * 8, 0);
#pragma unroll
        for (int f = 0; f < 16; f++) {
          const int r = ((f >> 1) * 4 + m * 2 + (f & 1)) * 4;
          ldmatrix4t((wfa ^ ((f & 1) * 32)) + (f >> 1) * 1024, wf[r], wf[r + 1], wf[r + 2], wf[r + 3]);
        }
      }
    }
    PROF(8, ct == PT, 31); STAMP(10);
    uint32_t kwin; int iwin;
    uint4 hv[8];
    uint32_t wd[64];
    const uint32_t wda = base + unit_of(FT_D, warp >> 1) + (warp & 1) * 8192 + frow * 128 + ((((ln >> 3) & 1) ^ (ln & 7)) << 4);
#define LOAD_WD(f) ldmatrix4t((wda ^ ((((f) >> 1) & 3) * 32)) + ((f) >> 3) * 4096 + ((f) & 1) * 2048, wd[4 * (f)], wd[4 * (f) + 1], wd[4 * (f) + 2], wd[4 * (f) + 3])
    {
      uint32_t n = 0;
      int cur = -1;
      while (true) {
        const bool valid = !(((cv.x ^ tag) | (cv.y ^ tag)) & 3u);
        const uint32_t key = valid ? cv.x : 0u;
        kwin = __reduce_max_sync(0xffffffffu, key);
        const int src = (__ffs(__ballot_sync(0xffffffffu, key == kwin)) - 1) & 15;
        if (kwin && src != cur) {
          cur = src;
#pragma unroll
          for (int i = 0; i < 8; i++) hv[i] = ld_pairs(g_row + cur * 2 * DM + warp * 128 + i * 16 + tq * 4);
        }
        if (__all_sync(0xffffffffu, valid)) break;
        cv = ld_relaxed2(inbox);
        watchdog(n);
      }
      iwin = __shfl_sync(0xffffffffu, cv.y, cur) >> 2;
    }
    PROF(8, ct == PT, 32); STAMP(11);
    const uint32_t* wrow = g_row + (iwin >> 7) * 2 * DM;
    if (b < NFFN) {
      {
        uint32_t n = 0;
        bool ok;
        do {
          ok = true;
#pragma unroll
          for (int i = 0; i < 8; i++)
            if (hv[i].y != tag || hv[i].w != tag) { hv[i] = ld_pairs(wrow + warp * 128 + i * 16 + tq * 4); ok = false; }
          watchdog(n);
        } while (!ok);
      }
      __syncwarp();
      PROF(8, ct == PT, 33); STAMP(12);
      float d[8][4];
#pragma unroll
      for (int i = 0; i < 8; i++) { d[i][0] = 0.f; d[i][1] = 0.f; d[i][2] = 0.f; d[i][3] = 0.f; }
#pragma unroll
      for (int ks = 0; ks < 8; ks++) {
#pragma unroll
        for (int mt = 0; mt < 4; mt++) {
          const int r = ks * 16 + mt * 4;
          mma16816(d[mt + (ks & 1) * 4], wf[r], wf[r + 1], wf[r + 2], wf[r + 3], hv[ks].x, hv[ks].z);
        }
        if (ks == 1) mbar_wait(bar_box + (8 + (warp >> 1)) * 8, 0);
        if (ks >= 1) {
#pragma unroll
          for (int f = 4 * ks - 4; f < 16 && f < 4 * ks; f++) LOAD_WD(f);
        }
      }
      if (tq == 0) {
        const uint32_t dst = base + unit_of(FT_G, warp >> 1) + (warp & 1) * 8192 + g * 32;
        sts4(dst, make_uint4(__float_as_uint(d[0][0] + d[4][0]), __float_as_uint(d[0][2] + d[4][2]), __float_as_uint(d[1][0] + d[5][0]), __float_as_uint(d[1][2] + d[5][2])));
        sts4(dst + 16, make_uint4(__float_as_uint(d[2][0] + d[6][0]), __float_as_uint(d[2][2] + d[6][2]), __float_as_uint(d[3][0] + d[7][0]), __float_as_uint(d[3][2] + d[7][2])));
      }
      bar_sync(1, 256);
      uint32_t ab[4];
      {
        float G = 0.f, U = 0.f;
        const uint32_t src = base + (ln & 7) * 32 + (ln >> 3) * 4;
#pragma unroll
        for (int w8 = 0; w8 < 8; w8++) {
          const uint32_t a = src + ((FT_G >> (w8 >> 1) * 4) & 15) * UNIT + (w8 & 1) * 8192;
          G += __uint_as_float(lds1(a)); U += __uint_as_float(lds1(a + 16));
        }
        const float act = rbf(silu_f(rbf(G))) * rbf(U);
        const uint32_t pk = pack_bf(act, __shfl_down_sync(0xffffffffu, act, 1));
#pragma unroll
        for (int i = 0; i < 4; i++) ab[i] = __shfl_sync(0xffffffffu, pk, i * 8 + tq * 2);
      }
      PROF(8, ct == PT, 34); STAMP(13);
#pragma unroll
      for (int mt = 0; mt < 8; mt++) {
        d[mt][0] = 0.f; d[mt][1] = 0.f; d[mt][2] = 0.f; d[mt][3] = 0.f;
        mma16816(d[mt], wd[mt * 8], wd[mt * 8 + 1], wd[mt * 8 + 2], wd[mt * 8 + 3], ab[0], ab[1]);
        mma16816(d[mt], wd[mt * 8 + 4], wd[mt * 8 + 5], wd[mt * 8 + 6], wd[mt * 8 + 7], ab[2], ab[3]);
      }
#pragma unroll
      for (int i = 0; i < 4; i++) {
        const int m4 = (i >> 1) * 4, e = (i & 1) * 2;
        const float y = (tq & 2) ? ((tq & 1) ? d[m4 + 3][e] : d[m4 + 2][e]) : ((tq & 1) ? d[m4 + 1][e] : d[m4][e]);
        st_relaxed(g_ypart + ((size_t)(warp * 16 + (m4 + tq) * 2 + (i & 1)) * NFFN + b) * 8 + g, tagf(y, tag));
      }
      PROF(8, ct == PT, 35); STAMP(14);
    }
    if (ct == 0) { sts2(par + PAR_CONST + 56, kwin, iwin); mbar_arrive(bar_win); }
    {
      const uint32_t mm0 = __shfl_sync(0xffffffffu, mm, ln & ~1), mm1 = __shfl_sync(0xffffffffu, mm, ln | 1);
      const uint32_t ih0 = __shfl_sync(0xffffffffu, ih, ln & ~1), ih1 = __shfl_sync(0xffffffffu, ih, ln | 1);
      const uint32_t il0 = __shfl_sync(0xffffffffu, il, ln & ~1), il1 = __shfl_sync(0xffffffffu, il, ln | 1);
      const bool mine = (iwin >> 4) == rb * 8 + warp;
#pragma unroll 1
      for (int hf = 0; hf < 2; hf++) {
        uint32_t x[16];
#pragma unroll
        for (int i = 0; i < 8; i += 2) ldmatrix4((trow ^ (i << 4)) + hf * 16384, x[2 * i], x[2 * i + 1], x[2 * i + 2], x[2 * i + 3]);
#pragma unroll
        for (int i = 0; i < 8; i++) {
          const uint4 pv = lds4(par + PAR_T2 + (hf * 8 + i) * 64 + tq * 16);
          x[2 * i] = hadd2(x[2 * i], hmul2(pv.z, ln_mod(x[2 * i], mm0, ih0, il0, pv.x, pv.y)));
          x[2 * i + 1] = hadd2(x[2 * i + 1], hmul2(pv.z, ln_mod(x[2 * i + 1], mm1, ih1, il1, pv.x, pv.y)));
        }
        if (mine) {
          uint32_t* dst = reinterpret_cast<uint32_t*>(P.out + (size_t)grow0 * DM + cj * 128 + hf * 64) + tq;
#pragma unroll
          for (int i = 0; i < 8; i++) {
            if (grow0 != iwin) dst[i * 4] = x[2 * i];
            if (grow0 + 8 != iwin) dst[i * 4 + 4 * DM] = x[2 * i + 1];
          }
        } else {
#pragma unroll
          for (int i = 0; i < 8; i += 2) stmatrix4((trow ^ (i << 4)) + hf * 16384, x[2 * i], x[2 * i + 1], x[2 * i + 2], x[2 * i + 3]);
          fence_async_smem();
          __syncwarp();
          if (elect_one()) {
            tma2d_store(&maps.out, res + hf * 16384 + warp * 2048, cj * 128 + hf * 64, rb * 128 + warp * 16);
            asm volatile("cp.async.bulk.commit_group;" ::: "memory");
          }
        }
      }
      asm volatile("cp.async.bulk.wait_group.read 0;" ::: "memory");
    }
    PROF(8, ct == PT, 11); STAMP(15);
    cluster_wait();
  }
}

typedef CUresult (*EncodeFn)(CUtensorMap*, CUtensorMapDataType, cuuint32_t, void*, const cuuint64_t*, const cuuint64_t*,
                             const cuuint32_t*, const cuuint32_t*, CUtensorMapInterleave, CUtensorMapSwizzle,
                             CUtensorMapL2promotion, CUtensorMapFloatOOBfill);

void map2d(EncodeFn enc, CUtensorMap* m, const void* p, uint64_t rows, uint64_t cols, uint32_t brows) {
  cuuint64_t dims[2] = {cols, rows}, strides[1] = {cols * 2};
  cuuint32_t box[2] = {64, brows}, es[2] = {1, 1};
  enc(m, CU_TENSOR_MAP_DATA_TYPE_BFLOAT16, 2, const_cast<void*>(p), dims, strides, box, es, CU_TENSOR_MAP_INTERLEAVE_NONE,
      CU_TENSOR_MAP_SWIZZLE_128B, CU_TENSOR_MAP_L2_PROMOTION_L2_256B, CU_TENSOR_MAP_FLOAT_OOB_FILL_NONE);
}
void map2d_narrow(EncodeFn enc, CUtensorMap* m, const void* p, uint64_t rows, uint64_t cols) {
  cuuint64_t dims[2] = {cols, rows}, strides[1] = {cols * 2};
  cuuint32_t box[2] = {32, 256}, es[2] = {1, 1};
  enc(m, CU_TENSOR_MAP_DATA_TYPE_BFLOAT16, 2, const_cast<void*>(p), dims, strides, box, es, CU_TENSOR_MAP_INTERLEAVE_NONE,
      CU_TENSOR_MAP_SWIZZLE_64B, CU_TENSOR_MAP_L2_PROMOTION_L2_64B, CU_TENSOR_MAP_FLOAT_OOB_FILL_NONE);
}
void map3d(EncodeFn enc, CUtensorMap* m, const void* p, uint64_t rows, uint64_t cols, uint32_t brows, uint32_t nch) {
  cuuint64_t dims[3] = {64, rows, cols / 64}, strides[2] = {cols * 2, 128};
  cuuint32_t box[3] = {64, brows, nch}, es[3] = {1, 1, 1};
  enc(m, CU_TENSOR_MAP_DATA_TYPE_BFLOAT16, 3, const_cast<void*>(p), dims, strides, box, es, CU_TENSOR_MAP_INTERLEAVE_NONE,
      CU_TENSOR_MAP_SWIZZLE_128B, CU_TENSOR_MAP_L2_PROMOTION_L2_256B, CU_TENSOR_MAP_FLOAT_OOB_FILL_NONE);
}

}

extern "C" void kernel_launch(void* const* d_in, const int* in_sizes, int n_in, void* d_out, int out_size) {
  (void)in_sizes; (void)n_in; (void)out_size;
  static EncodeFn enc = nullptr;
  if (!enc) {
    void* fn = nullptr;
    cudaDriverEntryPointQueryResult st;
    cudaGetDriverEntryPoint("cuTensorMapEncodeTiled", &fn, cudaEnableDefault, &st);
    enc = (EncodeFn)fn;
    cudaFuncSetAttribute(fused_kernel, cudaFuncAttributeMaxDynamicSharedMemorySize, SMEM_BYTES);
  }
  Maps maps;
  map2d(enc, &maps.x, d_in[0], SEQ, DM, 128);
  map2d(enc, &maps.out, d_out, SEQ, DM, 16);
  map3d(enc, &maps.wq, d_in[3], DM, NQ, 64, 2);
  map3d(enc, &maps.k, d_in[1], 4 * SK, 128, 128, 1);
  map3d(enc, &maps.v, d_in[2], 4 * SK, 128, 128, 1);
  map3d(enc, &maps.wo, d_in[4], NQ, DM, 64, 2);
  map2d_narrow(enc, &maps.wg, d_in[7], DM, FF);
  map2d_narrow(enc, &maps.wu, d_in[8], DM, FF);
  map3d(enc, &maps.wd, d_in[9], FF, DM, 32, 4);
  map2d_narrow(enc, &maps.wm, d_in[11], DM, NMOD);
  Ptrs p;
  p.x = (const __nv_bfloat16*)d_in[0];
  p.w_r = (const __nv_bfloat16*)d_in[6];
  p.w_gate = (const __nv_bfloat16*)d_in[7];
  p.w_up = (const __nv_bfloat16*)d_in[8];
  p.w_down = (const __nv_bfloat16*)d_in[9];
  p.c = (const __nv_bfloat16*)d_in[10];
  p.w_mod = (const __nv_bfloat16*)d_in[11];
  p.out = (__nv_bfloat16*)d_out;
  fused_kernel<<<NMAIN + NHELP, 384, SMEM_BYTES>>>(maps, p);
}
```

```cpp
#include <cuda_runtime.h>
#include <cuda_bf16.h>
#include <cuda.h>
#include <stdint.h>
#include <type_traits>

#define HD 1
#define HDX 2
#define XF 4
#define XE 32
#define XR 0
#define PF2 1
#define PF2T 4
#define NRS 6
#define FPACE 3
#define GOST 20
#define WB 2
#define WN 24
#define RES0 17
#define RES1 20
#define HU 32
#define NS1 6
#define PD0 40
#define PG0 31
#define PSL 120
#define WDE 4
#define VREL 7
#define E0 3

namespace {

constexpr int SEQ = 2048, DM = 1024, NQ = 4096, SK = 2048, WIN = 512, FF = 3584, NMOD = 6144;
constexpr int NMAIN = 128, NHELP = 4, NFFN = 112;
constexpr int NSLOT = 4, SLOT_BYTES = 32768, UNIT = 16384, GST_BYTES = 3 * UNIT;
constexpr uint32_t XT0 = 0x9630, XT1 = 0x54DC, XT2 = 0xDC96;
constexpr uint32_t WT0 = 0xA741, WT1 = 0x720A, WT2 = 0x20A7;
constexpr uint32_t AT0 = 0x7420, AT1 = 0x2C0A;
constexpr uint32_t QT = 0x549696DC;
constexpr int OFF_STAGE = 12 * UNIT;
constexpr uint32_t FT_G = 0x761B, FT_U = 0x0CA9, FT_D = 0x382D;
constexpr int OFF_RES = 4 * UNIT;
constexpr int OFF_PAR = 14 * UNIT;
constexpr int OFF_BAR = OFF_PAR + 2048 + 512;
constexpr int SMEM_BYTES = OFF_BAR + 512;
static_assert(SMEM_BYTES <= 232448, "smem");

constexpr int PAR_T1 = 0;
constexpr int PAR_T2 = 512;
constexpr int PAR_CONST = 1536;
constexpr int PAR_RED = 1600;
constexpr int PAR_SINK = 2176;

struct Maps {
  CUtensorMap x, wq, k, v, wo, wg, wu, wd, wm, out;
};
struct Ptrs {
  const __nv_bfloat16 *x, *w_r, *c, *w_mod, *w_gate, *w_up, *w_down;
  __nv_bfloat16* out;
};

__device__ __align__(1024) uint8_t g_act[16 * 80 * UNIT];
__device__ __align__(128) uint32_t g_mod[NMOD];
__device__ __align__(128) uint32_t g_modp[2 * 2 * DM];
__device__ __align__(128) uint32_t g_ln1[SEQ * 4];
__device__ __align__(128) uint32_t g_cnt_h[16 * 32];
__device__ __align__(128) uint32_t g_cnt_o[128 * 32];
__device__ __align__(128) uint32_t g_xch[NMAIN * 8 * 256 * 4];
__device__ __align__(128) uint32_t g_stats[8 * SEQ * 4];
__device__ __align__(128) uint32_t g_cand[NMAIN * 32];
__device__ __align__(128) uint32_t g_row[16 * 2 * DM];
__device__ __align__(128) uint32_t g_ypart[NMAIN * NFFN * 8];
__device__ uint32_t g_epoch;

__device__ __forceinline__ uint32_t fresh_lane() { uint32_t l; asm volatile("mov.u32 %0, %%laneid;" : "=r"(l)); return l; }
__device__ __forceinline__ uint32_t frag_offset(int warp) {
  const uint32_t l = fresh_lane();
  return ((warp & 3) * 16 + (l & 15)) * 128 + (((l >> 4) ^ (l & 7)) << 4);
}
__device__ __forceinline__ bool elect_one() {
  uint32_t p;
  asm volatile("{ .reg .pred q; elect.sync _|q, 0xffffffff; selp.u32 %0, 1, 0, q; }" : "=r"(p));
  return p;
}
__device__ __forceinline__ uint32_t smem_u32(const void* p) { return (uint32_t)__cvta_generic_to_shared(p); }
__device__ __forceinline__ void mbar_init(uint32_t bar, uint32_t cnt) {
  asm volatile("mbarrier.init.shared::cta.b64 [%0], %1;" ::"r"(bar), "r"(cnt) : "memory");
}
__device__ __forceinline__ void mbar_expect_tx(uint32_t bar, uint32_t bytes) {
  asm volatile("mbarrier.arrive.expect_tx.shared::cta.b64 _, [%0], %1;" ::"r"(bar), "r"(bytes) : "memory");
}
__device__ __forceinline__ void mbar_arrive(uint32_t bar) {
  asm volatile("mbarrier.arrive.shared::cta.b64 _, [%0];" ::"r"(bar) : "memory");
}
__device__ __forceinline__ void mbar_arrive_pred(uint32_t bar, bool p) {
  asm volatile("{ .reg .pred p; setp.ne.b32 p, %1, 0; @p mbarrier.arrive.shared::cta.b64 _, [%0]; }" ::"r"(bar), "r"((int)p) : "memory");
}
__device__ __forceinline__ void mbar_arrive_cl(uint32_t bar, uint32_t off, bool p = true) {
  asm volatile("{ .reg .pred p, q; .reg .b32 a; setp.ne.b32 q, %2, 0; setp.ne.and.b32 p, %0, 0, q; add.u32 a, %0, %1; @p mbarrier.arrive.shared::cluster.b64 _, [a]; }"
               ::"r"(bar), "r"(off), "r"((int)p) : "memory");
}
__device__ __forceinline__ uint32_t mapa(uint32_t addr, uint32_t cta) {
  uint32_t r; asm("mapa.shared::cluster.u32 %0, %1, %2;" : "=r"(r) : "r"(addr), "r"(cta)); return r;
}
__device__ __forceinline__ void cluster_arrive() { asm volatile("barrier.cluster.arrive.relaxed.aligned;" ::: "memory"); }
__device__ __forceinline__ void cluster_wait() { asm volatile("barrier.cluster.wait.aligned;" ::: "memory"); }
__device__ __forceinline__ void watchdog(uint32_t& n) {
}
__device__ __forceinline__ void mbar_wait(uint32_t bar, uint32_t parity) {
  asm volatile("{\n.reg .pred p;\nWAIT_%=:\nmbarrier.try_wait.parity.shared::cta.b64 p, [%0], %1;\n@!p bra WAIT_%=;\n}" ::"r"(bar), "r"(parity) : "memory");
}
__device__ __forceinline__ bool mbar_test(uint32_t bar, uint32_t parity) {
  uint32_t ok;
  asm volatile("{\n.reg .pred p;\nmbarrier.test_wait.parity.shared::cta.b64 p, [%1], %2;\nselp.u32 %0, 1, 0, p;\n}" : "=r"(ok) : "r"(bar), "r"(parity) : "memory");
  return ok;
}
__device__ __forceinline__ uint64_t l2_stream() {
  uint64_t f; asm("createpolicy.fractional.L2::evict_first.b64 %0, 1.0;" : "=l"(f)); return f;
}
__device__ __forceinline__ void tma2d(uint32_t dst, const CUtensorMap* m, int c0, int c1, uint32_t bar) {
  asm volatile("cp.async.bulk.tensor.2d.shared::cluster.global.mbarrier::complete_tx::bytes.L2::cache_hint [%0], [%1, {%3, %4}], [%2], %5;"
               ::"r"(dst), "l"(m), "r"(bar), "r"(c0), "r"(c1), "l"(l2_stream()) : "memory");
}
__device__ __forceinline__ void tma3d_prefetch(const CUtensorMap* m, int c0, int c1, int c2) {
  asm volatile("cp.async.bulk.prefetch.tensor.3d.L2.global.tile [%0, {%1, %2, %3}];" ::"l"(m), "r"(c0), "r"(c1), "r"(c2) : "memory");
}
__device__ __forceinline__ void bulk_load(uint32_t dst, const void* src, uint32_t bytes, uint32_t bar) {
  asm volatile("cp.async.bulk.shared::cluster.global.mbarrier::complete_tx::bytes [%0], [%1], %2, [%3];" ::"r"(dst), "l"(src), "r"(bytes), "r"(bar) : "memory");
}
__device__ __forceinline__ void bulk_load_stream(uint32_t dst, const void* src, uint32_t bytes, uint32_t bar) {
  asm volatile("cp.async.bulk.shared::cluster.global.mbarrier::complete_tx::bytes.L2::cache_hint [%0], [%1], %2, [%3], %4;"
               ::"r"(dst), "l"(src), "r"(bytes), "r"(bar), "l"(l2_stream()) : "memory");
}
__device__ __forceinline__ void tma2d_store(const CUtensorMap* m, uint32_t src, int c0, int c1) {
  asm volatile("cp.async.bulk.tensor.2d.global.shared::cta.bulk_group [%0, {%2, %3}], [%1];" ::"l"(m), "r"(src), "r"(c0), "r"(c1) : "memory");
}
__device__ __forceinline__ void bulk_store(void* dst, uint32_t src, uint32_t bytes) {
  asm volatile("cp.async.bulk.global.shared::cta.bulk_group [%0], [%1], %2;" ::"l"(dst), "r"(src), "r"(bytes) : "memory");
}
__device__ __forceinline__ uint32_t unit_of(uint32_t table, uint32_t i) { return ((table >> (i * 4)) & 15) * UNIT; }
__device__ __forceinline__ void tma3d(uint32_t dst, const CUtensorMap* m, int c0, int c1, int c2, uint32_t bar) {
  asm volatile("cp.async.bulk.tensor.3d.shared::cluster.global.mbarrier::complete_tx::bytes.L2::cache_hint [%0], [%1, {%3, %4, %5}], [%2], %6;"
               ::"r"(dst), "l"(m), "r"(bar), "r"(c0), "r"(c1), "r"(c2), "l"(l2_stream()) : "memory");
}
template <bool STREAM>
__device__ __forceinline__ void tma3d_mc(uint32_t dst, const CUtensorMap* m, int c0, int c1, int c2, uint32_t bar) {
  if (STREAM)
    asm volatile("cp.async.bulk.tensor.3d.shared::cluster.global.mbarrier::complete_tx::bytes.multicast::cluster.L2::cache_hint [%0], [%1, {%3, %4, %5}], [%2], %6, %7;"
                 ::"r"(dst), "l"(m), "r"(bar), "r"(c0), "r"(c1), "r"(c2), "h"((uint16_t)3), "l"(l2_stream()) : "memory");
  else
    asm volatile("cp.async.bulk.tensor.3d.shared::cluster.global.mbarrier::complete_tx::bytes.multicast::cluster [%0], [%1, {%3, %4, %5}], [%2], %6;"
                 ::"r"(dst), "l"(m), "r"(bar), "r"(c0), "r"(c1), "r"(c2), "h"((uint16_t)3) : "memory");
}
__device__ __forceinline__ void prefetch_map(const CUtensorMap* m) {
  asm volatile("prefetch.tensormap [%0];" ::"l"(m) : "memory");
}
__device__ __forceinline__ void fence_async() { asm volatile("fence.proxy.async.global;" ::: "memory"); }
__device__ __forceinline__ void fence_async_smem() { asm volatile("fence.proxy.async.shared::cta;" ::: "memory"); }
__device__ __forceinline__ void bar_sync(int id, int n) { asm volatile("bar.sync %0, %1;" ::"r"(id), "r"(n) : "memory"); }
__device__ __forceinline__ void bar_arrive(int id, int n) { asm volatile("bar.arrive %0, %1;" ::"r"(id), "r"(n) : "memory"); }
__device__ __forceinline__ void wg_fence() { asm volatile("wgmma.fence.sync.aligned;" ::: "memory"); }
__device__ __forceinline__ void wg_commit() { asm volatile("wgmma.commit_group.sync.aligned;" ::: "memory"); }
template <int N> __device__ __forceinline__ void wg_wait() { asm volatile("wgmma.wait_group.sync.aligned %0;" ::"n"(N) : "memory"); }
__device__ __forceinline__ uint64_t make_desc(uint32_t addr, uint32_t lbo, uint32_t sbo) {
  return (uint64_t)((addr & 0x3FFFF) >> 4) | ((uint64_t)(lbo >> 4) << 16) | ((uint64_t)(sbo >> 4) << 32) | (1ull << 62);
}
__device__ __forceinline__ uint32_t ld_relaxed(const uint32_t* p) {
  uint32_t v; asm volatile("ld.relaxed.gpu.global.u32 %0, [%1];" : "=r"(v) : "l"(p) : "memory"); return v;
}
__device__ __forceinline__ uint32_t ld_acquire(const uint32_t* p) {
  uint32_t v; asm volatile("ld.acquire.gpu.global.u32 %0, [%1];" : "=r"(v) : "l"(p) : "memory"); return v;
}
__device__ __forceinline__ uint4 ld_relaxed4(const uint32_t* p) {
  uint4 v; asm volatile("ld.relaxed.gpu.global.v4.u32 {%0,%1,%2,%3}, [%4];" : "=r"(v.x), "=r"(v.y), "=r"(v.z), "=r"(v.w) : "l"(p) : "memory"); return v;
}
__device__ __forceinline__ uint2 ld_relaxed2(const uint32_t* p) {
  uint2 v; asm volatile("ld.relaxed.gpu.global.v2.u32 {%0,%1}, [%2];" : "=r"(v.x), "=r"(v.y) : "l"(p) : "memory"); return v;
}
__device__ __forceinline__ void st_relaxed(uint32_t* p, uint32_t v) {
  asm volatile("st.relaxed.gpu.global.u32 [%0], %1;" ::"l"(p), "r"(v) : "memory");
}
__device__ __forceinline__ void st_relaxed2(uint32_t* p, uint32_t a, uint32_t b) {
  asm volatile("st.relaxed.gpu.global.v2.u32 [%0], {%1,%2};" ::"l"(p), "r"(a), "r"(b) : "memory");
}
__device__ __forceinline__ void st_relaxed4(uint32_t* p, uint32_t a, uint32_t b, uint32_t c, uint32_t d) {
  asm volatile("st.relaxed.gpu.global.v4.u32 [%0], {%1,%2,%3,%4};" ::"l"(p), "r"(a), "r"(b), "r"(c), "r"(d) : "memory");
}
__device__ __forceinline__ void st_b128(uint32_t* p, uint32_t a, uint32_t b, uint32_t c, uint32_t d) {
  asm volatile("{ .reg .b64 u, v; .reg .b128 w; mov.b64 u, {%1, %2}; mov.b64 v, {%3, %4}; mov.b128 w, {u, v}; st.relaxed.gpu.global.b128 [%0], w; }"
               ::"l"(p), "r"(a), "r"(b), "r"(c), "r"(d) : "memory");
}
__device__ __forceinline__ uint4 ld_b128(const uint32_t* p) {
  uint4 r;
  asm volatile("{ .reg .b64 u, v; .reg .b128 w; ld.relaxed.gpu.global.b128 w, [%4]; mov.b128 {u, v}, w; mov.b64 {%0, %1}, u; mov.b64 {%2, %3}, v; }"
               : "=r"(r.x), "=r"(r.y), "=r"(r.z), "=r"(r.w) : "l"(p) : "memory");
  return r;
}
__device__ __forceinline__ void st_pairs(uint32_t* p, uint32_t a, uint32_t b, uint32_t tag) {
  asm volatile("{ .reg .b64 u, v; mov.b64 u, {%1, %3}; mov.b64 v, {%2, %3}; st.relaxed.gpu.global.v2.b64 [%0], {u, v}; }"
               ::"l"(p), "r"(a), "r"(b), "r"(tag) : "memory");
}
__device__ __forceinline__ uint4 ld_pairs(const uint32_t* p) {
  uint4 v;
  asm volatile("{ .reg .b64 u, v; ld.relaxed.gpu.global.v2.b64 {u, v}, [%4]; mov.b64 {%0, %1}, u; mov.b64 {%2, %3}, v; }"
               : "=r"(v.x), "=r"(v.y), "=r"(v.z), "=r"(v.w) : "l"(p) : "memory");
  return v;
}
__device__ __forceinline__ uint2 ld_pair(const uint32_t* p) {
  uint2 v;
  asm volatile("{ .reg .b64 u; ld.relaxed.gpu.global.b64 u, [%2]; mov.b64 {%0, %1}, u; }" : "=r"(v.x), "=r"(v.y) : "l"(p) : "memory");
  return v;
}
__device__ __forceinline__ void red_release(uint32_t* p, uint32_t v) {
  asm volatile("red.release.gpu.global.add.u32 [%0], %1;" ::"l"(p), "r"(v) : "memory");
}
__device__ __forceinline__ uint32_t ldg_nc1(const void* p) {
  uint32_t v;
  asm volatile("ld.global.nc.u32 %0, [%1];" : "=r"(v) : "l"(p));
  return v;
}
__device__ __forceinline__ uint4 ldg_nc4(const void* p) {
  uint4 v; asm volatile("ld.global.nc.L1::no_allocate.v4.u32 {%0,%1,%2,%3}, [%4];" : "=r"(v.x), "=r"(v.y), "=r"(v.z), "=r"(v.w) : "l"(p)); return v;
}
__device__ __forceinline__ uint4 ldg_stream4(const void* p) {
  uint4 v;
  asm volatile("ld.global.nc.L1::no_allocate.L2::cache_hint.v4.u32 {%0,%1,%2,%3}, [%4], %5;" : "=r"(v.x), "=r"(v.y), "=r"(v.z), "=r"(v.w) : "l"(p), "l"(l2_stream()));
  return v;
}
__device__ __forceinline__ void stg4(void* p, uint4 v) {
  asm volatile("st.global.v4.u32 [%0], {%1,%2,%3,%4};" ::"l"(p), "r"(v.x), "r"(v.y), "r"(v.z), "r"(v.w) : "memory");
}
__device__ __forceinline__ void wait_counter(const uint32_t* p, uint32_t target) {
  uint32_t n = 0;
  while ((int)(ld_acquire(p) - target) < 0) { watchdog(n); }
}
__device__ __forceinline__ uint32_t tagf(float v, uint32_t tag) { return (__float_as_uint(v) & ~3u) | tag; }
__device__ __forceinline__ bool tag_ok(uint4 v, uint32_t tag) { return (((v.x ^ tag) | (v.y ^ tag) | (v.z ^ tag) | (v.w ^ tag)) & 3u) == 0; }
__device__ __forceinline__ float untag_sum(uint32_t a, uint32_t b) { return __uint_as_float(a & ~3u) + __uint_as_float(b & ~3u); }
__device__ __forceinline__ uint4 poll4(const uint32_t* p, uint32_t tag) {
  uint4 v = ld_relaxed4(p);
  uint32_t n = 0;
  while (!tag_ok(v, tag)) { v = ld_relaxed4(p); watchdog(n); }
  return v;
}
__device__ __forceinline__ float bf_lo(uint32_t v) { return __uint_as_float(v << 16); }
__device__ __forceinline__ float bf_hi(uint32_t v) { return __uint_as_float(v & 0xffff0000u); }
__device__ __forceinline__ uint32_t pack_bf(float lo, float hi) {
  uint32_t r; asm("cvt.rn.bf16x2.f32 %0, %1, %2;" : "=r"(r) : "f"(hi), "f"(lo)); return r;
}
__device__ __forceinline__ float rbf(float v) { return __uint_as_float(pack_bf(0.f, v) & 0xffff0000u); }
__device__ __forceinline__ uint32_t hmul2(uint32_t a, uint32_t b) {
  uint32_t r; asm("mul.rn.bf16x2 %0, %1, %2;" : "=r"(r) : "r"(a), "r"(b)); return r;
}
__device__ __forceinline__ uint32_t hadd2(uint32_t a, uint32_t b) {
  uint32_t r; asm("add.rn.bf16x2 %0, %1, %2;" : "=r"(r) : "r"(a), "r"(b)); return r;
}
__device__ __forceinline__ uint32_t hsub2(uint32_t a, uint32_t b) {
  uint32_t r; asm("sub.rn.bf16x2 %0, %1, %2;" : "=r"(r) : "r"(a), "r"(b)); return r;
}
__device__ __forceinline__ uint32_t hmax2(uint32_t a, uint32_t b) {
  uint32_t r; asm("max.bf16x2 %0, %1, %2;" : "=r"(r) : "r"(a), "r"(b)); return r;
}
__device__ __forceinline__ float rcp(float x) { float r; asm("rcp.approx.ftz.f32 %0, %1;" : "=f"(r) : "f"(x)); return r; }
__device__ __forceinline__ float ex2(float x) { float r; asm("ex2.approx.ftz.f32 %0, %1;" : "=f"(r) : "f"(x)); return r; }
__device__ __forceinline__ void stmatrix4(uint32_t addr, uint32_t a, uint32_t b, uint32_t c, uint32_t d) {
  asm volatile("stmatrix.sync.aligned.m8n8.x4.shared.b16 [%0], {%1,%2,%3,%4};" ::"r"(addr), "r"(a), "r"(b), "r"(c), "r"(d) : "memory");
}
__device__ __forceinline__ void ldmatrix4(uint32_t addr, uint32_t& a, uint32_t& b, uint32_t& c, uint32_t& d) {
  asm volatile("ldmatrix.sync.aligned.m8n8.x4.shared.b16 {%0,%1,%2,%3}, [%4];" : "=r"(a), "=r"(b), "=r"(c), "=r"(d) : "r"(addr) : "memory");
}
__device__ __forceinline__ void ldmatrix4t(uint32_t addr, uint32_t& a, uint32_t& b, uint32_t& c, uint32_t& d) {
  asm volatile("ldmatrix.sync.aligned.m8n8.x4.trans.shared.b16 {%0,%1,%2,%3}, [%4];" : "=r"(a), "=r"(b), "=r"(c), "=r"(d) : "r"(addr) : "memory");
}
__device__ __forceinline__ void mma16816(float (&d)[4], uint32_t a0, uint32_t a1, uint32_t a2, uint32_t a3, uint32_t b0, uint32_t b1) {
  asm volatile("mma.sync.aligned.m16n8k16.row.col.f32.bf16.bf16.f32 {%0,%1,%2,%3}, {%4,%5,%6,%7}, {%8,%9}, {%0,%1,%2,%3};"
               : "+f"(d[0]), "+f"(d[1]), "+f"(d[2]), "+f"(d[3]) : "r"(a0), "r"(a1), "r"(a2), "r"(a3), "r"(b0), "r"(b1));
}
__device__ __forceinline__ void sts1(uint32_t a, uint32_t v) { asm volatile("st.shared.u32 [%0], %1;" ::"r"(a), "r"(v) : "memory"); }
__device__ __forceinline__ uint4 lds4(uint32_t a) {
  uint4 v; asm volatile("ld.shared.v4.u32 {%0,%1,%2,%3}, [%4];" : "=r"(v.x), "=r"(v.y), "=r"(v.z), "=r"(v.w) : "r"(a) : "memory"); return v;
}
__device__ __forceinline__ uint2 lds2(uint32_t a) {
  uint2 v; asm volatile("ld.shared.v2.u32 {%0,%1}, [%2];" : "=r"(v.x), "=r"(v.y) : "r"(a) : "memory"); return v;
}
__device__ __forceinline__ uint32_t lds1(uint32_t a) {
  uint32_t v; asm volatile("ld.shared.u32 %0, [%1];" : "=r"(v) : "r"(a) : "memory"); return v;
}
__device__ __forceinline__ void sts2(uint32_t a, uint32_t x, uint32_t y) { asm volatile("st.shared.v2.u32 [%0], {%1,%2};" ::"r"(a), "r"(x), "r"(y) : "memory"); }
__device__ __forceinline__ void sts4(uint32_t a, uint4 v) {
  asm volatile("st.shared.v4.u32 [%0], {%1,%2,%3,%4};" ::"r"(a), "r"(v.x), "r"(v.y), "r"(v.z), "r"(v.w) : "memory");
}
__device__ __forceinline__ float silu_f(float v) { return __fdividef(v, 1.f + __expf(-v)); }
__device__ __forceinline__ uint32_t hfma2(uint32_t a, uint32_t b, uint32_t c) {
  uint32_t r; asm("fma.rn.bf16x2 %0, %1, %2, %3;" : "=r"(r) : "r"(a), "r"(b), "r"(c)); return r;
}
__device__ __forceinline__ void split_inv(float sd, uint32_t& ih, uint32_t& il) {
  const float inv = rcp(sd);
  ih = pack_bf(inv, inv);
  const float lo = inv - bf_lo(ih);
  il = pack_bf(lo, lo);
}
__device__ __forceinline__ uint32_t ln_mod(uint32_t x, uint32_t mean2, uint32_t ih, uint32_t il, uint32_t c1, uint32_t sh) {
  const uint32_t d = hsub2(x, mean2);
  return hadd2(hmul2(hfma2(d, ih, hmul2(d, il)), c1), sh);
}

#define R8(a, i) "+f"(a[i]), "+f"(a[i + 1]), "+f"(a[i + 2]), "+f"(a[i + 3]), "+f"(a[i + 4]), "+f"(a[i + 5]), "+f"(a[i + 6]), "+f"(a[i + 7])
#define D64 "{%0,%1,%2,%3,%4,%5,%6,%7,%8,%9,%10,%11,%12,%13,%14,%15,%16,%17,%18,%19,%20,%21,%22,%23,%24,%25,%26,%27,%28,%29,%30,%31," \
            "%32,%33,%34,%35,%36,%37,%38,%39,%40,%41,%42,%43,%44,%45,%46,%47,%48,%49,%50,%51,%52,%53,%54,%55,%56,%57,%58,%59,%60,%61,%62,%63}"
template <int TB>
__device__ __forceinline__ void mma_ss(float (&d)[64], uint64_t da, uint64_t db, int sc) {
  asm volatile("{\n.reg .pred p;\nsetp.ne.b32 p, %66, 0;\n"
               "wgmma.mma_async.sync.aligned.m64n128k16.f32.bf16.bf16 " D64 ", %64, %65, p, 1, 1, 0, %67;\n}"
               : R8(d, 0), R8(d, 8), R8(d, 16), R8(d, 24), R8(d, 32), R8(d, 40), R8(d, 48), R8(d, 56)
               : "l"(da), "l"(db), "r"(sc), "n"(TB));
}
template <int TB>
__device__ __forceinline__ void mma_rs(float (&d)[64], uint32_t a0, uint32_t a1, uint32_t a2, uint32_t a3, uint64_t db, int sc) {
  asm volatile("{\n.reg .pred p;\nsetp.ne.b32 p, %69, 0;\n"
               "wgmma.mma_async.sync.aligned.m64n128k16.f32.bf16.bf16 " D64 ", {%64,%65,%66,%67}, %68, p, 1, 1, %70;\n}"
               : R8(d, 0), R8(d, 8), R8(d, 16), R8(d, 24), R8(d, 32), R8(d, 40), R8(d, 48), R8(d, 56)
               : "r"(a0), "r"(a1), "r"(a2), "r"(a3), "l"(db), "r"(sc), "n"(TB));
}
#define D128 "{%0,%1,%2,%3,%4,%5,%6,%7,%8,%9,%10,%11,%12,%13,%14,%15,%16,%17,%18,%19,%20,%21,%22,%23,%24,%25,%26,%27,%28,%29,%30,%31," \
             "%32,%33,%34,%35,%36,%37,%38,%39,%40,%41,%42,%43,%44,%45,%46,%47,%48,%49,%50,%51,%52,%53,%54,%55,%56,%57,%58,%59,%60,%61,%62,%63," \
             "%64,%65,%66,%67,%68,%69,%70,%71,%72,%73,%74,%75,%76,%77,%78,%79,%80,%81,%82,%83,%84,%85,%86,%87,%88,%89,%90,%91,%92,%93,%94,%95," \
             "%96,%97,%98,%99,%100,%101,%102,%103,%104,%105,%106,%107,%108,%109,%110,%111,%112,%113,%114,%115,%116,%117,%118,%119,%120,%121,%122,%123,%124,%125,%126,%127}"
#define R128(d, e) R8(d, 0), R8(d, 8), R8(d, 16), R8(d, 24), R8(d, 32), R8(d, 40), R8(d, 48), R8(d, 56), \
                   R8(e, 0), R8(e, 8), R8(e, 16), R8(e, 24), R8(e, 32), R8(e, 40), R8(e, 48), R8(e, 56)
__device__ __forceinline__ void mma256_ss(float (&d)[64], float (&e)[64], uint64_t da, uint64_t db, int sc) {
  asm volatile("{\n.reg .pred p;\nsetp.ne.b32 p, %130, 0;\n"
               "wgmma.mma_async.sync.aligned.m64n256k16.f32.bf16.bf16 " D128 ", %128, %129, p, 1, 1, 0, 1;\n}"
               : R128(d, e) : "l"(da), "l"(db), "r"(sc));
}
__device__ __forceinline__ void mma256_rs(float (&d)[64], float (&e)[64], uint32_t a0, uint32_t a1, uint32_t a2, uint32_t a3, uint64_t db) {
  asm volatile("{\n.reg .pred p;\nsetp.ne.b32 p, 1, 0;\n"
               "wgmma.mma_async.sync.aligned.m64n256k16.f32.bf16.bf16 " D128 ", {%128,%129,%130,%131}, %132, p, 1, 1, 1;\n}"
               : R128(d, e) : "r"(a0), "r"(a1), "r"(a2), "r"(a3), "l"(db));
}
template <int N> __device__ __forceinline__ void keep(float (&a)[N]) {
#pragma unroll
  for (int i = 0; i < N; i++) asm volatile("" : "+f"(a[i])::"memory");
}
template <int N> __device__ __forceinline__ void keep(uint32_t (&a)[N]) {
#pragma unroll
  for (int i = 0; i < N; i++) asm volatile("" : "+r"(a[i])::"memory");
}

#define STAMP(idx) do {} while (0)
#define PROF(grp, cond, idx) do {} while (0)

constexpr float SCL2 = 1.4426950408889634f * 0.08838834764831845f;

__device__ __forceinline__ void pack_p(const float (&s)[64], uint32_t (&p)[32]) {
#pragma unroll
  for (int i = 0; i < 32; i++) p[i] = pack_bf(s[2 * i], s[2 * i + 1]);
}

__device__ __forceinline__ void issue_qk(float (&s)[64], uint32_t q0, uint32_t q1, uint32_t kslot) {
  const uint64_t db = make_desc(kslot, 16, 1024), da0 = make_desc(q0, 16, 1024), da1 = make_desc(q1, 16, 1024);
#pragma unroll
  for (int kk = 0; kk < 8; kk++) mma_ss<0>(s, (kk < 4 ? da0 : da1) + (kk & 3) * 2, db + (kk >> 2) * 1024 + (kk & 3) * 2, kk != 0);
}
__device__ __forceinline__ void issue_pv(float (&o)[64], uint32_t (&p)[32], uint32_t vslot, int acc) {
  uint64_t db = make_desc(vslot, 16384, 1024);
#pragma unroll
  for (int kk = 0; kk < 8; kk++)
    mma_rs<1>(o, p[4 * kk], p[4 * kk + 1], p[4 * kk + 2], p[4 * kk + 3], db + kk * 128, kk == 0 ? acc : 1);
}

template <int H>
__device__ __forceinline__ void store_chunk(const float (&a)[64], uint32_t addr) {
#pragma unroll
  for (int i = 8 * H; i < 8 * H + 8; i += 2)
    stmatrix4(addr ^ ((i & 7) << 4), pack_bf(a[4 * i], a[4 * i + 1]), pack_bf(a[4 * i + 2], a[4 * i + 3]),
              pack_bf(a[4 * i + 4], a[4 * i + 5]), pack_bf(a[4 * i + 6], a[4 * i + 7]));
}
template <int H>
__device__ __forceinline__ void store_chunk(const float (&a)[64], float i0, float i1, uint32_t addr) {
#pragma unroll
  for (int i = 8 * H; i < 8 * H + 8; i += 2)
    stmatrix4(addr ^ ((i & 7) << 4), pack_bf(a[4 * i] * i0, a[4 * i + 1] * i0), pack_bf(a[4 * i + 2] * i1, a[4 * i + 3] * i1),
              pack_bf(a[4 * i + 4] * i0, a[4 * i + 5] * i0), pack_bf(a[4 * i + 6] * i1, a[4 * i + 7] * i1));
}
__device__ __forceinline__ float inv_quad_sum(float l) {
  l += __shfl_xor_sync(0xffffffffu, l, 1);
  l += __shfl_xor_sync(0xffffffffu, l, 2);
  return rcp(l);
}

__device__ __forceinline__ void ln_scalars(float mean, float var, float& mb, float& sd) {
  mb = rbf(mean);
  float r; asm("sqrt.approx.ftz.f32 %0, %1;" : "=f"(r) : "f"(rbf(rbf(var) + 1e-5f)));
  sd = rbf(r);
}

__global__ void __cluster_dims__(2, 1, 1) __launch_bounds__(384, 1) fused_kernel(const __grid_constant__ Maps maps, const Ptrs P) {
  extern __shared__ __align__(1024) uint8_t smem_raw[];
  const uint32_t base = smem_u32(smem_raw);
  const int tid = threadIdx.x, lane = tid & 31;
  const int warp = __shfl_sync(0xffffffffu, tid >> 5, 0);
  const int b = blockIdx.x;
  PROF(31, tid == 0, 0);

  if (b >= NMAIN) {
    float* sc = reinterpret_cast<float*>(smem_raw);
    float* red = sc + DM;
    for (int k = tid; k < DM; k += 384) sc[k] = rbf(silu_f(__bfloat162float(P.c[k])));
    __syncthreads();
    if (tid < 256) {
      const int col = 2048 + (b - NMAIN) * 1024 + (tid & 127) * 8, r0 = (tid >> 7) * 512;
      float acc[8];
#pragma unroll
      for (int e = 0; e < 8; e++) acc[e] = 0.f;
#pragma unroll 1
      for (int r = r0; r < r0 + 512; r += HU) {
        uint4 w[HU];
#pragma unroll
        for (int u = 0; u < HU; u++) w[u] = ldg_stream4(P.w_mod + (size_t)(r + u) * NMOD + col);
#pragma unroll
        for (int u = 0; u < HU; u++) {
          float s = sc[r + u];
          acc[0] += s * bf_lo(w[u].x); acc[1] += s * bf_hi(w[u].x); acc[2] += s * bf_lo(w[u].y); acc[3] += s * bf_hi(w[u].y);
          acc[4] += s * bf_lo(w[u].z); acc[5] += s * bf_hi(w[u].z); acc[6] += s * bf_lo(w[u].w); acc[7] += s * bf_hi(w[u].w);
        }
      }
      if (tid >= 128) {
#pragma unroll
        for (int e = 0; e < 8; e++) red[(tid & 127) * 8 + e] = acc[e];
      }
      const uint32_t tag = ld_relaxed(&g_epoch) % 3 + 1;
      bar_sync(1, 256);
      if (tid < 128) {
        uint32_t o[8];
#pragma unroll
        for (int e = 0; e < 8; e++) o[e] = __float_as_uint(rbf(acc[e] + red[tid * 8 + e])) | tag;
        st_relaxed4(g_mod + col, o[0], o[1], o[2], o[3]);
        st_relaxed4(g_mod + col + 4, o[4], o[5], o[6], o[7]);
        const uint4 wr = ldg_nc4(P.w_r + tid * 8);
        const uint32_t wv[4] = {wr.x, wr.y, wr.z, wr.w};
        float dsum = 0.f;
#pragma unroll
        for (int e = 0; e < 8; e++) {
          const float m = bf_hi(o[e]);
          dsum += (b == NMAIN + 2 ? rbf(1.f + m) : m) * ((e & 1) ? bf_hi(wv[e >> 1]) : bf_lo(wv[e >> 1]));
        }
#pragma unroll
        for (int k = 16; k > 0; k >>= 1) dsum += __shfl_xor_sync(0xffffffffu, dsum, k);
        if (lane == 0) st_relaxed(g_mod + (b - NMAIN) * 4 + warp, tagf(dsum, tag));
      }
    }
    PROF(2, tid == 0, 1);
    return;
  }

  const int rank = b & 1;
  const int rb = ((b >> 4) << 1) | rank, cj = (b >> 1) & 7;
  const uint32_t bfull = base + OFF_BAR, bempty = bfull + NSLOT * 8;
  const uint32_t gfull = bempty + NSLOT * 8, gempty = gfull + 32;
  const uint32_t bar_ofull = gempty + 32;
  const uint32_t bar_ofree = bar_ofull + 16;
  const uint32_t bar_par = bar_ofree + 32;
  const uint32_t bar_mod = bar_par + 8;
  const uint32_t bar_pread = bar_mod + 8;
  const uint32_t bar_xres = bar_pread + 8;
  const uint32_t bar_ring = bar_xres + 8;
  const uint32_t bar_box = bar_ring + 24;
  const uint32_t bar_go = bar_box + 96;
  const uint32_t bar_go2 = bar_go + 16;
  const uint32_t bar_cnt = bar_go + 24;
  const uint32_t xfull = bar_go + 32, xempty = xfull + 32;
  const uint32_t bar_hw = xempty + 32, bar_hx = bar_hw + 8;
  const uint32_t bar_hpub = bar_hx + 16;
  const uint32_t bar_win = bar_hpub + 8;
  const uint32_t bar_rx = bar_win + 8;
  const uint32_t bar_sel = bar_rx + 8;
  const uint32_t bar_gate = bar_sel + 8;
  const uint32_t bar_res = bar_go + 8;
  const uint32_t stage = base + OFF_STAGE, par = base + OFF_PAR;

  if (warp == 8 && elect_one()) {
    for (int s = 0; s < NSLOT; s++) { mbar_init(bfull + s * 8, 1); mbar_init(bempty + s * 8, 16); }
    for (int s = 0; s < 4; s++) { mbar_init(gfull + s * 8, 1); mbar_init(gempty + s * 8, 16); mbar_init(xfull + s * 8, 1); mbar_init(xempty + s * 8, 8); mbar_init(bar_ofree + s * 8, 1); }
    mbar_init(bar_ofull, 128); mbar_init(bar_ofull + 8, 128);
    mbar_init(bar_par, 64); mbar_init(bar_mod, 256); mbar_init(bar_pread, 8); mbar_init(bar_xres, 1);
    mbar_init(bar_ring, 8); mbar_init(bar_ring + 8, 8); mbar_init(bar_ring + 16, 8);
    mbar_init(bar_go, 1); mbar_init(bar_go2, 1); mbar_init(bar_cnt, 1); mbar_init(bar_hpub, 8); mbar_init(bar_res, 1); mbar_init(bar_win, 1); mbar_init(bar_rx, 1); mbar_init(bar_sel, 64); mbar_init(bar_gate, 8);
    for (int s = 0; s < 12; s++) mbar_init(bar_box + s * 8, 1);
    asm volatile("fence.mbarrier_init.release.cluster;" ::: "memory");
    prefetch_map(&maps.x); prefetch_map(&maps.wq); prefetch_map(&maps.k); prefetch_map(&maps.v);
  }
  if (warp == 9 && elect_one()) {
    mbar_init(bar_hw, 1); mbar_init(bar_hx, 1); mbar_init(bar_hx + 8, 1);
    asm volatile("fence.mbarrier_init.release.cluster;" ::: "memory");
    mbar_expect_tx(bar_hw, 32768);
    mbar_expect_tx(bar_hx, 16384);
    mbar_expect_tx(bar_hx + 8, 16384);
    const __nv_bfloat16* xs = P.x + (size_t)(rb * 128 + cj * 16) * DM;
    bulk_load(base + 2 * GST_BYTES, xs, 16384, bar_hx);
    tma2d(stage, &maps.wm, (b >> 1) * 32, rank * 512, bar_hw);
    tma2d(stage + 16384, &maps.wm, (b >> 1) * 32, rank * 512 + 256, bar_hw);
    bulk_load(base + 3 * GST_BYTES, xs + 8 * DM, 16384, bar_hx + 8);
  }
  cluster_arrive();

  if (warp >= 8) {
    asm volatile("setmaxnreg.dec.sync.aligned.u32 40;");
    if (warp < 10) bar_arrive(1, 320);
    const uint32_t epoch = ld_relaxed(&g_epoch);
    cluster_wait();
    if (warp == 8) {
      const int kvrow = (cj >> 1) * SK + (SK - WIN);
      int wch = cj * 8 + rank * 2;
#pragma unroll 1
      for (int ps = 0; ps < 3; ps++) {
        const CUtensorMap* mw = ps == 2 ? &maps.wo : &maps.wq;
        const uint32_t xt = ps == 1 ? XT1 : XT2, wt = ps == 0 ? WT0 : (ps == 1 ? WT1 : WT2);
        const int nst = ps == 2 ? 32 : 16;
        if (ps) {
          mbar_wait(bar_ofree + (ps - 1) * 16, 0);
          fence_async();
        }
#pragma unroll 1
        for (int i = 0; i < nst; i++) {
          const uint32_t bf = gfull + (i & 3) * 8;
          const int kt = ps == 2 ? (((cj & 1) * 4 + ((i >> 1) & 3)) * 4 + (i >> 3)) * 2 + (i & 1) : (i + (ps ? 0 : b & 14)) & 15;
          const uint32_t wd = base + unit_of(wt, i & 3) + rank * UNIT, xd = base + unit_of(xt, i & 3);
          const uint8_t* xs = g_act + (uint32_t)(rb * 80 + (ps - 1) * 16 + kt) * UNIT;
          if (ps == 0 && i == HD) mbar_wait(bar_mod, 0);
          if (ps && i && i < 4) mbar_wait(bempty + (i == 3 ? 3 : i - 1) * 8, 1);
          mbar_wait(gempty + (i & 3) * 8, ((i >> 2) & 1) ^ 1);
          if (elect_one()) {
            mbar_expect_tx(bf, ps ? GST_BYTES : 2 * UNIT);
            tma3d_mc<true>(wd, mw, 0, (i == 31 ? kt ^ (rank * 32) : kt) * 64, i == 31 ? cj * 2 : wch, bf);
          }
          if (ps) {
            if (i == 16) mbar_wait(bar_cnt, 0);
            if (i == 2) mbar_wait(bempty + 16, 1);
            if (elect_one()) {
              if (i == 31) bulk_load(xd, xs, UNIT, bf); else bulk_load_stream(xd, xs, UNIT, bf);
              mbar_arrive_pred(bar_go, i == GOST - 1);
              mbar_arrive_pred(bar_go2, ps * 16 + i == PG0);
              mbar_arrive_pred(bar_res, ((1u << RES0 | 1u << RES1) >> i) & 1);
              if (ps == 2 && b < NFFN && i >= PD0 && i < PD0 + 16)
                asm volatile("cp.async.bulk.prefetch.L2.global [%0], 4096;" ::"l"(P.w_down + (size_t)b * 32768 + (i - PD0) * 2048) : "memory");
            }
          }
        }
        if (ps == 2) break;
        wch = ps ? ((wch >> 3) ^ rank) * 2 : wch + 4;
#pragma unroll 1
        for (int u = 0; u < 16; u++) {
          const bool isk = (u == 0) || ((u & 1) && u < 15);
          const int blk = (isk ? (u + 1) >> 1 : (u == 15 ? 7 : (u >> 1) - 1)) & 3;
          const uint32_t sl = base + unit_of(ps ? AT1 : AT0, u & 3) + rank * UNIT, bf = bfull + (u & 3) * 8;
          if (u < 4) mbar_wait(gempty + ((u + 1) >> 1) * 8, 1);
          mbar_wait(bempty + (u & 3) * 8, ((u >> 2) & 1) ^ 1);
          if (elect_one()) {
            mbar_expect_tx(bf, SLOT_BYTES);
            tma3d_mc<false>(sl, isk ? &maps.k : &maps.v, 0, kvrow + blk * 128, rank, bf);
            if (ps && u >= PF2T && u < PF2T + 2 * PF2 && !((u - PF2T) & 1))
              tma3d_prefetch(&maps.wo, 0, ((((cj & 1) * 4 + (b >> 5)) * 4 + ((u - PF2T) >> 1)) * 2 + ((b >> 4) & 1)) * 64, (cj ^ rank) * 2);
          }
        }
      }
      mbar_wait(bar_ring, 0);
      if (elect_one()) {
        mbar_expect_tx(bar_rx, UNIT);
        bulk_load_stream(base + 8 * UNIT, g_act + (uint32_t)(rb * 80 + 16 + 63 - (cj & 1) * 32) * UNIT, UNIT, bar_rx);
      }
      if (b < NFFN) {
#pragma unroll 1
        for (int u = 0; u < 12; u++) {
          if (u == 2 || u == 8) mbar_wait(bar_ring + 8 + (u & 8), 0);
          if (u >= FPACE) mbar_wait(bar_box + (u - FPACE) * 8, 0);
          const uint32_t dst = base + unit_of(u < 4 ? FT_G : (u < 8 ? FT_U : FT_D), u & 3);
          if (elect_one()) {
            mbar_expect_tx(bar_box + u * 8, UNIT);
            if (u < 8) tma2d(dst, u < 4 ? &maps.wg : &maps.wu, b * 32, (u & 3) * 256, bar_box + u * 8);
            else tma3d(dst, &maps.wd, 0, b * 32, (u - 8) * 4, bar_box + u * 8);
          }
        }
      }
    } else if (warp == 9) {
      const uint32_t target = 8 * (epoch + 1);
#pragma unroll 1
      for (int i = 0; i < 16; i++) {
        if (i == HDX) mbar_wait(bar_mod, 0);
        if (i == NRS) {
          wait_counter(&g_cnt_h[rb * 32], target);
          PROF(1, lane == 0, 26);
          fence_async();
        }
        mbar_wait(xempty + (i & 3) * 8, ((i >> 2) & 1) ^ 1);
        if (elect_one()) {
          mbar_expect_tx(xfull + (i & 3) * 8, UNIT);
          if (i < NRS) tma2d(base + (i & 3) * GST_BYTES, &maps.x, ((2 * cj + i) & 15) * 64, rb * 128, xfull + (i & 3) * 8);
          else bulk_load_stream(base + (i & 3) * GST_BYTES, g_act + (uint32_t)(rb * 80 + ((2 * cj + i) & 15)) * UNIT, UNIT, xfull + (i & 3) * 8);
        }
      }
      prefetch_map(&maps.wo);
#pragma unroll 1
      for (int t = 0; t < 4; t++) {
#pragma unroll 1
        for (int w = 0; w < 2; w++) {
          mbar_wait(bar_ofull + w * 8, t & 1);
          uint8_t* dst = g_act + (uint32_t)(rb * 80 + 16 + (cj * 4 + t) * 2) * UNIT + w * 8192;
          if (elect_one()) {
            bulk_store(dst, base + unit_of(QT, 2 * t) + w * 8192, 8192);
            bulk_store(dst + UNIT, base + unit_of(QT, 2 * t + 1) + w * 8192, 8192);
            asm volatile("cp.async.bulk.commit_group;" ::: "memory");
          }
        }
        if (elect_one()) {
          asm volatile("cp.async.bulk.wait_group.read 0;" ::: "memory");
          mbar_arrive(bar_ofree + t * 8);
          asm volatile("cp.async.bulk.wait_group 0;" ::: "memory");
          fence_async();
          red_release(&g_cnt_o[((rb * 4 + t) * 2 + (cj >> 2)) * 32], 2);
        }
        if (t & 1) {
          wait_counter(&g_cnt_o[(rb * 8 + 2 * t - 2 + (cj & 1)) * 32], target);
          wait_counter(&g_cnt_o[(rb * 8 + 2 * t + (cj & 1)) * 32], target);
        }
      }
      wait_counter(&g_cnt_o[(rb * 8 + 7 - (cj & 1)) * 32], target);
      fence_async();
      if (elect_one()) {
        mbar_arrive(bar_cnt);
        PROF(2, true, 27);
        mbar_expect_tx(bar_xres, 32768);
      }
#pragma unroll 1
      for (int u = 0; u < 2; u++) {
        mbar_wait(bar_res, u);
        if (elect_one()) tma2d(base + OFF_RES + u * UNIT, &maps.x, cj * 128 + u * 64, rb * 128, bar_xres);
      }
      const uint32_t tag = epoch % 3 + 1;
      const uint32_t* inbox = g_cand + b * 32 + (lane & 15);
      mbar_wait(bar_ring + 16, 0);
      uint32_t c0 = ld_relaxed(inbox);
      __nanosleep(PSL);
      uint32_t c1 = ld_relaxed(inbox);
      __nanosleep(PSL);
      uint32_t c2 = ld_relaxed(inbox), n = 0;
#define CAND_STEP(cv)                                                                                        \
      {                                                                                                      \
        const bool valid = (cv & 3u) == tag, all = __all_sync(0xffffffffu, valid);                           \
        const uint32_t best = __reduce_max_sync(0xffffffffu, valid ? cv : 0u);                               \
        const uint32_t blk = __ffs(__ballot_sync(0xffffffffu, cv == best)) - 1;                              \
        if (best) sts2(par + PAR_CONST + 56, best, (blk << 7 | (~best >> 2 & 127)) | (all ? 0x1800 : 0x800)); \
        if (all) break;                                                                                      \
        cv = ld_relaxed(inbox);                                                                              \
      }
      while (true) { CAND_STEP(c0) CAND_STEP(c1) CAND_STEP(c2) watchdog(n); }
    } else {
      const int t2 = tid - 320;
      if (t2 == 0) {
        mbar_wait(bar_hpub, 0);
        PROF(1, true, 24);
        red_release(&g_cnt_h[rb * 32], 1);
        PROF(1, true, 25);
        prefetch_map(&maps.wg); prefetch_map(&maps.wu); prefetch_map(&maps.wd); prefetch_map(&maps.out);
      }
      __syncwarp();
      if (b < NFFN) {
        mbar_wait(bar_go2, 0);
        const __nv_bfloat16* pg = ((b & 1) ? P.w_up : P.w_gate) + (b >> 1) * 64 + (size_t)t2 * FF;
        const __nv_bfloat16* pd = P.w_down + (size_t)b * 32768 + t2 * 64;
        PROF(2, t2 == 0, 13);
#pragma unroll 1
        for (int i = 0; i < WN; i += WB) {
          uint32_t v[WB];
#pragma unroll
          for (int u = 0; u < WB; u++)
            asm volatile("ld.global.cg.L2::128B.u32 %0, [%1];" : "=r"(v[u]) : "l"(i < 16 ? pg + (size_t)(i + u) * 64 * FF : pd + (i + u - 16) * 4096));
#pragma unroll
          for (int u = 1; u < WB; u++) v[0] ^= v[u];
          sts1(par + PAR_SINK + t2 * 4, v[0]);
        }
        PROF(2, t2 == 0, 14);
      }
      const uint32_t tag = epoch % 3 + 1;
      mbar_wait(bar_go, 0);
      if (warp == 10) {
        const uint32_t* src = g_mod + 2 * DM + cj * 128 + lane * 4;
        const uint2 wr = *reinterpret_cast<const uint2*>(P.w_r + cj * 128 + lane * 4);
        uint4 vga, vsb, vcb, vgb;
        uint32_t n = 0;
        do {
          vga = ld_relaxed4(src); vsb = ld_relaxed4(src + DM); vcb = ld_relaxed4(src + 2 * DM); vgb = ld_relaxed4(src + 3 * DM);
          watchdog(n);
        } while (!(tag_ok(vga, tag) && tag_ok(vsb, tag) && tag_ok(vcb, tag) && tag_ok(vgb, tag)));
        const float c0 = rbf(1.f + bf_hi(vcb.x)), c1 = rbf(1.f + bf_hi(vcb.y)), c2 = rbf(1.f + bf_hi(vcb.z)), c3 = rbf(1.f + bf_hi(vcb.w));
        const float a0 = c0 * bf_lo(wr.x), a1 = c1 * bf_hi(wr.x), a2 = c2 * bf_lo(wr.y), a3 = c3 * bf_hi(wr.y);
        const uint32_t h0 = pack_bf(a0, a1), h1 = pack_bf(a2, a3);
        const uint32_t t1 = par + PAR_T1 + (lane >> 2) * 64 + (lane & 1) * 32 + (lane & 2) * 2;
        sts1(t1, h0); sts1(t1 + 8, pack_bf(a0 - bf_lo(h0), a1 - bf_hi(h0)));
        sts1(t1 + 16, h1); sts1(t1 + 24, pack_bf(a2 - bf_lo(h1), a3 - bf_hi(h1)));
        sts4(par + PAR_T2 + lane * 32, make_uint4(pack_bf(c0, c1), __byte_perm(vsb.x, vsb.y, 0x7632), __byte_perm(vgb.x, vgb.y, 0x7632), __byte_perm(vga.x, vga.y, 0x7632)));
        sts4(par + PAR_T2 + lane * 32 + 16, make_uint4(pack_bf(c2, c3), __byte_perm(vsb.z, vsb.w, 0x7632), __byte_perm(vgb.z, vgb.w, 0x7632), __byte_perm(vga.z, vga.w, 0x7632)));
      } else if (lane < 4) {
        const uint4 g = poll4(lane < 2 ? g_mod + 5 * DM + b * 8 + lane * 4 : g_mod + 16 - lane * 4, tag);
        sts1(par + PAR_CONST + 60, 0);
        if (lane < 2) sts4(par + PAR_CONST + 16 + lane * 16, g);
        else sts2(par + PAR_CONST + (lane - 2) * 8, __float_as_uint(untag_sum(g.x, g.y) + untag_sum(g.z, g.w)), epoch);
      }
      __syncwarp();
#pragma unroll 4
      for (int q = XR; q < XE; q++) st_b128(g_xch + ((size_t)b * 8 * 256 + q * 64 + t2) * 4, (epoch & 1) << 16, 0, 0, 0);
      for (int q = 0; q < 2; q++) st_relaxed4(g_stats + ((size_t)cj * SEQ + rb * 128 + q * 64 + t2) * 4, 0, 0, 0, 0);
      if (b < NFFN)
        for (int q = 0; q < 4; q++) st_relaxed4(g_ypart + ((size_t)(q * 32 + (t2 >> 1)) * NFFN + b) * 8 + (t2 & 1) * 4, 0, 0, 0, 0);
      st_relaxed4(g_row + rb * 2 * DM + (t2 >> 5) * DM + cj * 128 + (t2 & 31) * 4, 0, 0, 0, 0);
      if (t2 < 16) st_relaxed(g_cand + (cj * 16 + t2) * 32 + rb, 0);
      __threadfence();
      mbar_arrive(bar_par);
      mbar_wait(bar_gate, 0);
      uint32_t have = 0, n = 0;
      while (true) {
        const uint32_t st = lds1(par + PAR_CONST + 60) >> 7;
        if ((st & 31) != have) {
          const uint32_t* hsrc = g_row + (st & 15) * 2 * DM + t2 * 4;
          uint4 hv[4];
          bool ok = true;
#pragma unroll
          for (int i = 0; i < 4; i++) hv[i] = ld_pairs(hsrc + i * 256);
#pragma unroll
          for (int i = 0; i < 4; i++) {
            sts2(base + ((FT_G >> i * 4) & 15) * UNIT + (warp & 1) * 8192 + 256 + lane * 8, hv[i].x, hv[i].z);
            ok = ok && hv[i].y == tag && hv[i].w == tag;
          }
          have = __all_sync(0xffffffffu, ok) ? st & 31 : 0;
        }
        if ((st ^ have) == 32) break;
        watchdog(n);
      }
      mbar_arrive(bar_sel);
    }
    __syncwarp();
    cluster_arrive();
    {
      const uint32_t tag = epoch % 3 + 1, t3 = tid - 256;
      mbar_wait(bar_win, 0);
      uint2 win = lds2(par + PAR_CONST + 56);
      win.y &= 0x7ff;
      const uint32_t* fsrc = g_row + (win.y >> 7) * 2 * DM + (b >> 1) * 16 + (t3 & 3) * 4 + (b & 1) * 2;
      const uint32_t* ysrc = g_ypart + ((size_t)b * NFFN + min(t3, NFFN - 1)) * 8;
      uint2 fh = ld_pair(fsrc), fx = ld_pair(fsrc + DM);
      uint4 ya = ld_relaxed4(ysrc), yb = ld_relaxed4(ysrc + 4);
      const float rwin = __uint_as_float(((int)win.x < 0 ? win.x & 0x7fffffffu : ~win.x) & ~0x1ffu);
      const float rs = rbf(rcp(1.f + __expf(-rbf(rwin))));
      uint32_t n = 0;
      while (fh.y != tag || fx.y != tag) { fh = ld_pair(fsrc); fx = ld_pair(fsrc + DM); watchdog(n); }
      while (!(tag_ok(ya, tag) && tag_ok(yb, tag))) { ya = ld_relaxed4(ysrc); yb = ld_relaxed4(ysrc + 4); watchdog(n); }
      __syncwarp();
      PROF(8, t3 == 0, 5);
      const uint32_t msk = t3 < NFFN ? ~3u : 0u;
      float y[8] = {__uint_as_float(ya.x & msk), __uint_as_float(ya.y & msk), __uint_as_float(ya.z & msk), __uint_as_float(ya.w & msk),
                    __uint_as_float(yb.x & msk), __uint_as_float(yb.y & msk), __uint_as_float(yb.z & msk), __uint_as_float(yb.w & msk)};
#pragma unroll
      for (int h = 4; h > 0; h >>= 1) {
        const bool up = lane & (h * 4);
#pragma unroll
        for (int e = 0; e < h; e++) y[e] = (up ? y[e + h] : y[e]) + __shfl_xor_sync(0xffffffffu, up ? y[e] : y[e + h], h * 4);
      }
      y[0] += __shfl_xor_sync(0xffffffffu, y[0], 1);
      y[0] += __shfl_xor_sync(0xffffffffu, y[0], 2);
      if ((lane & 3) == 0) sts1(par + PAR_RED + 64 + t3, __float_as_uint(y[0]));
      bar_sync(4, 128);
      if (t3 < 4) {
        float y0 = 0.f, y1 = 0.f;
#pragma unroll
        for (int w4 = 0; w4 < 4; w4++) {
          const uint2 v = lds2(par + PAR_RED + 64 + w4 * 32 + t3 * 8);
          y0 += __uint_as_float(v.x); y1 += __uint_as_float(v.y);
        }
        const uint2 gv = lds2(par + PAR_CONST + 16 + t3 * 8);
        const uint32_t upd = hmul2(pack_bf(y0, y1), pack_bf(rs, rs));
        *reinterpret_cast<uint32_t*>(P.out + (size_t)win.y * DM + b * 8 + t3 * 2) =
            hadd2(fx.x, hmul2(__byte_perm(gv.x, gv.y, 0x7632), hadd2(fh.x, upd)));
        if (b == 0 && t3 == 0) st_relaxed(&g_epoch, epoch + 1);
      }
      PROF(31, t3 == 0, 36);
    }
    cluster_wait();
  } else {
    const int wg = warp >> 2;

    uint32_t tag;
    {
      uint32_t* const pmod = g_modp + rank * 2 * DM + (b >> 1) * 32 + lane;
      uint32_t* const pln = g_ln1 + (rb * 128 + cj * 16 + warp) * 4;
      const uint32_t cv = ldg_nc1(P.c + rank * 512 + tid * 2);
      const uint32_t epoch = ld_relaxed(&g_epoch);
      if (warp == 0) st_relaxed(pmod, 0);
      if (lane == 0) { st_relaxed2(pln, 0, 0); st_relaxed2(pln + 32, 0, 0); }
      asm volatile("setmaxnreg.inc.sync.aligned.u32 232;");
      sts1(par + tid * 4, pack_bf(silu_f(bf_lo(cv)), silu_f(bf_hi(cv))));
      bar_sync(1, 320);
      tag = epoch % 3 + 1;
#pragma unroll
      for (int part = 0; part < 3; part++) {
        if (part != 1) {
          const uint32_t xa = base + (2 + part / 2) * GST_BYTES + warp * 2048 + lane * 16;
          mbar_wait(bar_hx + part * 4, 0);
          float s0 = 0.f, s1 = 0.f, q0 = 0.f, q1 = 0.f;
#pragma unroll
          for (int q = 0; q < 4; q++) {
            const uint4 xv = lds4(xa + q * 512);
            const uint32_t u[4] = {xv.x, xv.y, xv.z, xv.w};
#pragma unroll
            for (int e = 0; e < 4; e++) { const float lo = bf_lo(u[e]), hi = bf_hi(u[e]); s0 += lo; s1 += hi; q0 += lo * lo; q1 += hi * hi; }
          }
          s0 += s1; q0 += q1;
#pragma unroll
          for (int o = 16; o > 0; o >>= 1) { s0 += __shfl_xor_sync(0xffffffffu, s0, o); q0 += __shfl_xor_sync(0xffffffffu, q0, o); }
          const float mean = s0 * (1.f / DM);
          float mb, sd;
          ln_scalars(mean, fmaxf(q0 * (1.f / DM) - mean * mean, 0.f), mb, sd);
          if (lane == 0) st_relaxed2(pln + part * 16, __float_as_uint(mb) | tag, __float_as_uint(sd) | tag);
          PROF(1, tid == 0 && part == 2, 4);
        } else {
          float acc[8];
#pragma unroll
          for (int e = 0; e < 8; e++) acc[e] = 0.f;
          const uint32_t wa = stage + (tid >> 2) * 64 + (((tid ^ (tid >> 3)) & 3) << 4), sa = par + (tid >> 3) * 4, sh = (tid & 4) ? 0x3244 : 0x1044;
          mbar_wait(bar_hw, 0);
#pragma unroll
          for (int p = 0; p < 8; p++) {
            const uint4 w = lds4(wa + p * 4096);
            const float s = __uint_as_float(__byte_perm(lds1(sa + p * 128), 0, sh));
            acc[0] += s * bf_lo(w.x); acc[1] += s * bf_hi(w.x); acc[2] += s * bf_lo(w.y); acc[3] += s * bf_hi(w.y);
            acc[4] += s * bf_lo(w.z); acc[5] += s * bf_hi(w.z); acc[6] += s * bf_lo(w.w); acc[7] += s * bf_hi(w.w);
          }
#pragma unroll
          for (int e = 0; e < 4; e++) {
            const bool up = lane & 16;
            acc[e] = (up ? acc[e + 4] : acc[e]) + __shfl_xor_sync(0xffffffffu, up ? acc[e] : acc[e + 4], 16);
          }
#pragma unroll
          for (int e = 0; e < 2; e++) {
            const bool up = lane & 8;
            acc[e] = (up ? acc[e + 2] : acc[e]) + __shfl_xor_sync(0xffffffffu, up ? acc[e] : acc[e + 2], 8);
          }
          {
            const bool up = lane & 4;
            acc[0] = (up ? acc[1] : acc[0]) + __shfl_xor_sync(0xffffffffu, up ? acc[0] : acc[1], 4);
          }
          sts1(par + 1024 + warp * 128 + ((lane & 3) * 8 + (lane >> 2)) * 4, __float_as_uint(acc[0]));
          bar_sync(1, 256);
          if (warp == 0) {
            float s = 0.f;
#pragma unroll
            for (int w8 = 0; w8 < 8; w8++) s += __uint_as_float(lds1(par + 1024 + w8 * 128 + lane * 4));
            st_relaxed(pmod, (__float_as_uint(s) & ~3u) | tag);
          }
          PROF(1, tid == 0, 3);
        }
      }
      {
        uint2 s0 = ld_relaxed2(g_ln1 + (rb * 128 + (tid & 127)) * 4);
        uint4 v[4];
#pragma unroll
        for (int q = 0; q < 4; q++) v[q] = ld_relaxed4(g_modp + q * DM + tid * 4);
        {
          uint32_t n = 0;
          while (!(tag_ok(v[0], tag) && tag_ok(v[1], tag) && tag_ok(v[2], tag) && tag_ok(v[3], tag))) {
#pragma unroll
            for (int q = 0; q < 4; q++)
              if (!tag_ok(v[q], tag)) v[q] = ld_relaxed4(g_modp + q * DM + tid * 4);
            if (((s0.x ^ tag) | (s0.y ^ tag)) & 3u) s0 = ld_relaxed2(g_ln1 + (rb * 128 + (tid & 127)) * 4);
            watchdog(n);
          }
        }
        const uint32_t d = stage + (tid >> 2) * 64 + (tid & 1) * 32 + (tid & 2) * 2;
        sts1(d, pack_bf(1.f + rbf(untag_sum(v[1].x, v[3].x)), 1.f + rbf(untag_sum(v[1].y, v[3].y))));
        sts1(d + 16, pack_bf(1.f + rbf(untag_sum(v[1].z, v[3].z)), 1.f + rbf(untag_sum(v[1].w, v[3].w))));
        sts1(d + 8, pack_bf(untag_sum(v[0].x, v[2].x), untag_sum(v[0].y, v[2].y)));
        sts1(d + 24, pack_bf(untag_sum(v[0].z, v[2].z), untag_sum(v[0].w, v[2].w)));
        if (wg == 0) {
          uint32_t n = 0;
          while (((s0.x ^ tag) | (s0.y ^ tag)) & 3u) { s0 = ld_relaxed2(g_ln1 + (rb * 128 + tid) * 4); watchdog(n); }
          uint32_t ih, il;
          split_inv(bf_hi(s0.y), ih, il);
          sts4(stage + 4096 + tid * 16, make_uint4(__byte_perm(s0.x, 0, 0x3232), ih, il, 0));
        }
        mbar_arrive(bar_mod);
      }
      cluster_wait();
      if (wg == 1) bar_arrive(2, 256);
      mbar_wait(bar_mod, 0);
      PROF(1, tid == 0, 2);
    }

    float f0 = 0.f, f1 = 0.f;
    const uint32_t rempty = lane < 2 ? mapa(bempty, lane & 1) : 0;
    constexpr uint32_t GE = NSLOT * 8 + 32;
    float o[64], s[64];
#pragma unroll 1
    for (int ps = 0; ps < 3; ps++) {
      {
        const uint32_t xt = ps == 1 ? XT1 : XT2, wt = ps == 1 ? WT1 : WT2;
        const int nst = ps == 2 ? 28 : 14;
        if (ps == 0) {
          float ga[64], gb[64];
#pragma unroll
          for (int i = 0; i < 64; i++) { ga[i] = 0.f; gb[i] = 0.f; }
          uint32_t a[2][16];
          const uint32_t l = fresh_lane();
          const uint4 r0 = lds4(stage + 4096 + (warp * 16 + (l >> 2)) * 16), r1 = lds4(stage + 4096 + 128 + (warp * 16 + (l >> 2)) * 16);
          auto transform = [&](int i, uint32_t (&f)[16], uint32_t z) {
            const uint32_t ad = base + (i & 3) * GST_BYTES + wg * 8192 + frag_offset(warp) + z;
            mbar_wait(xfull + (i & 3) * 8, i >> 2);
#pragma unroll
            for (int kk = 0; kk < 4; kk++) ldmatrix4(ad ^ (kk * 32), f[4 * kk], f[4 * kk + 1], f[4 * kk + 2], f[4 * kk + 3]);
#pragma unroll
            for (int kk = 0; kk < 4; kk++) {
              const uint4 m = lds4(stage + (l & 3) * 16 + ((2 * cj + i) & 15) * 256 + kk * 64);
              f[4 * kk] = ln_mod(f[4 * kk], r0.x, r0.y, r0.z, m.x, m.z);
              f[4 * kk + 1] = ln_mod(f[4 * kk + 1], r1.x, r1.y, r1.z, m.x, m.z);
              f[4 * kk + 2] = ln_mod(f[4 * kk + 2], r0.x, r0.y, r0.z, m.y, m.w);
              f[4 * kk + 3] = ln_mod(f[4 * kk + 3], r1.x, r1.y, r1.z, m.y, m.w);
            }
            keep(f);
            mbar_arrive_pred(xempty + (i & 3) * 8, l == 0);
          };
          auto publish = [&](int u, uint32_t (&f)[16]) {
            const uint32_t sc = stage + 8192 + wg * 8192;
#pragma unroll
            for (int kk = 0; kk < 4; kk++) stmatrix4((sc + frag_offset(warp)) ^ (kk * 32), f[4 * kk], f[4 * kk + 1], f[4 * kk + 2], f[4 * kk + 3]);
            __syncwarp();
            const uint32_t src = sc + (warp & 3) * 2048 + l * 16;
            uint8_t* dst = g_act + (uint32_t)(rb * 80 + cj * 2 + u) * UNIT + warp * 2048 + l * 16;
#pragma unroll
            for (int p4 = 0; p4 < 4; p4++) stg4(dst + p4 * 512, lds4(src + p4 * 512));
            __syncwarp();
            if (u == 1) mbar_arrive_pred(bar_hpub, l == 0);
          };
          auto multiply = [&](int i, uint32_t (&f)[16]) {
            mbar_wait(gfull + (i & 3) * 8, i >> 2);
            const uint64_t db = make_desc(base + (i & 3) * GST_BYTES + UNIT, 8192, 1024);
            wg_fence();
#pragma unroll
            for (int kk = 0; kk < 4; kk++) mma256_rs(ga, gb, f[4 * kk], f[4 * kk + 1], f[4 * kk + 2], f[4 * kk + 3], db + kk * 128);
            wg_commit();
          };
          transform(0, a[0], 0); publish(0, a[0]); transform(1, a[1], 0); multiply(0, a[0]); publish(1, a[1]);
#pragma unroll
          for (int i = 1; i < NRS; i++) {
            if (i >= 2) {
              uint32_t z = r0.w;
#pragma unroll
              for (int k = 0; k < 16; k += 2) asm volatile("lop3.b32 %0, %1, %2, %0, 0xA8;" : "+r"(z) : "r"(a[i & 1][k]), "r"(a[i & 1][k + 1]));
              transform(i, a[i & 1], z);
            }
            multiply(i, a[i & 1]);
            wg_wait<1>();
            mbar_arrive_cl(rempty, GE + ((i + 3) & 3) * 8);
          }
          mbar_arrive_pred(bar_pread, l == 0);
#pragma unroll 1
          for (int i = NRS; i < 14; i++) {
            mbar_wait(xfull + (i & 3) * 8, (i >> 2) & 1);
            mbar_wait(gfull + (i & 3) * 8, (i >> 2) & 1);
            const uint32_t xa = base + (i & 3) * GST_BYTES;
            const uint64_t da = make_desc(xa + wg * 8192, 16, 1024), db = make_desc(xa + UNIT, 8192, 1024);
            if (i == 13) bar_sync(2 + wg, 256);
            wg_fence();
#pragma unroll
            for (int kk = 0; kk < 4; kk++) mma256_ss(ga, gb, da + kk * 2, db + kk * 128, 1);
            wg_commit();
            if (i == 13) bar_arrive(3 - wg, 256);
            wg_wait<1>();
            uint32_t z = r0.w;
#pragma unroll
            for (int k = 0; k < 16; k += 2) asm volatile("lop3.b32 %0, %1, %2, %0, 0xA8;" : "+r"(z) : "r"(a[1][k]), "r"(a[1][k + 1]));
            mbar_arrive_cl(rempty, GE + ((i + 3) & 3) * 8 + z);
            mbar_arrive_pred(xempty + ((i + 3) & 3) * 8, l == 0 && i != NRS);
          }
          mbar_wait(xfull + 16, 1);
          mbar_wait(xfull + 24, 1);
          wg_wait<0>();
          keep(ga); keep(gb);
#pragma unroll
          for (int i = 0; i < 64; i++) {
            asm volatile("mov.b32 %0, %1;" : "=f"(s[i]) : "f"(ga[i]));
            asm volatile("mov.b32 %0, %1;" : "=f"(o[i]) : "f"(gb[i]));
          }
        } else {
          float ga[64], gb[64];
#pragma unroll
          for (int i = 0; i < 64; i++) {
            asm volatile("mov.b32 %0, %1;" : "=f"(ga[i]) : "f"(s[i]));
            asm volatile("mov.b32 %0, %1;" : "=f"(gb[i]) : "f"(o[i]));
          }
#pragma unroll 1
          for (int i = 0; i < nst; i++) {
            mbar_wait(gfull + (i & 3) * 8, (i >> 2) & 1);
            const uint64_t da = make_desc(base + unit_of(xt, i & 3) + wg * 8192, 16, 1024), db = make_desc(base + unit_of(wt, i & 3), 8192, 1024);
            if (i == nst - 1) bar_sync(2 + wg, 256);
            wg_fence();
#pragma unroll
            for (int kk = 0; kk < 4; kk++) mma256_ss(ga, gb, da + kk * 2, db + kk * 128, kk ? 1 : i);
            wg_commit();
            if (i == nst - 1) bar_arrive(3 - wg, 256);
            wg_wait<1>();
            mbar_arrive_cl(rempty, GE + ((i + 3) & 3) * 8, i != 0);
            PROF(4, tid == 0 && (i & 3) == 0, 40 + (ps - 1) * 4 + i / 4);
          }
          wg_wait<0>();
          keep(ga); keep(gb);
#pragma unroll
          for (int i = 0; i < 64; i++) {
            asm volatile("mov.b32 %0, %1;" : "=f"(s[i]) : "f"(ga[i]));
            asm volatile("mov.b32 %0, %1;" : "=f"(o[i]) : "f"(gb[i]));
          }
        }
        mbar_arrive_cl(rempty, GE + (ps == 2 ? 24 : 8));
        if (ps == 2) break;
      }
      const uint32_t qw = base + wg * 8192, qt = QT >> (16 * ps), at = ps ? AT1 : AT0;
      {
        const uint32_t wt = ps ? WT1 : WT0;
        const uint64_t da0 = make_desc(qw + unit_of(qt, 2), 16, 1024), da1 = make_desc(qw + unit_of(qt, 3), 16, 1024);
        const uint64_t db0 = make_desc(base + unit_of(wt, 2), 8192, 1024), db1 = make_desc(base + unit_of(wt, 3), 8192, 1024);
        mbar_wait(gfull + 16, 1);
        mbar_wait(gfull + 24, 1);
        bar_sync(2 + wg, 256);
        wg_fence();
#pragma unroll
        for (int kk = 0; kk < 8; kk++) mma_ss<1>(s, (kk < 4 ? da0 : da1) + (kk & 3) * 2, (kk < 4 ? db0 : db1) + (kk & 3) * 128, 1);
        wg_commit();
        bar_arrive(3 - wg, 256);
        mbar_wait(ps == 0 ? bar_pread : bar_ofree + 8, 0);
        mbar_wait(bfull, 0);
        wg_wait<0>();
        keep(s);
        PROF(2, tid == 0, 8 + ps * 8);
        store_chunk<0>(s, qw + unit_of(qt, 0) + frag_offset(warp));
        store_chunk<1>(s, qw + unit_of(qt, 1) + frag_offset(warp));
        fence_async_smem();
        bar_sync(2 + wg, 256);
        wg_fence();
        issue_qk(s, qw + unit_of(qt, 0), qw + unit_of(qt, 1), base + unit_of(at, 0));
        wg_commit();
#pragma unroll
        for (int kk = 0; kk < 8; kk++) mma_ss<1>(o, (kk < 4 ? da0 : da1) + (kk & 3) * 2, (kk < 4 ? db0 : db1) + UNIT / 16 + (kk & 3) * 128, 1);
        wg_commit();
        bar_arrive(3 - wg, 256);
        wg_wait<1>();
        keep(s);
        mbar_arrive_cl(rempty, 0);
      }
      PROF(4, tid == 0 && ps == 1, 61);
      float l0 = 0.25f, l1 = 0.25f;
      auto step = [&](auto odd_c, const int j, uint32_t (&pw)[32], uint32_t (&pr)[32]) {
        constexpr bool ODD = decltype(odd_c)::value;
        const bool first = !ODD && (j & 2) == 0, last = ODD && j == 7;
        const uint32_t ph = (j >> 1) & 1;
        float i0, i1, a0, a1;
        if (first) { i0 = inv_quad_sum(l0); i1 = inv_quad_sum(l1); l0 = 0.f; l1 = 0.f; }
        bool redo = !ODD && (j | ps) == 0, again = false;
        while (true) {
          if (redo) {
            float m0 = fmaxf(s[0], s[1]), m1 = fmaxf(s[2], s[3]);
#pragma unroll
            for (int i = 1; i < 16; i++) { m0 = fmaxf(m0, fmaxf(s[4 * i], s[4 * i + 1])); m1 = fmaxf(m1, fmaxf(s[4 * i + 2], s[4 * i + 3])); }
            m0 = fmaxf(m0, __shfl_xor_sync(0xffffffffu, m0, 1)); m1 = fmaxf(m1, __shfl_xor_sync(0xffffffffu, m1, 1));
            m0 = fmaxf(m0, __shfl_xor_sync(0xffffffffu, m0, 2)); m1 = fmaxf(m1, __shfl_xor_sync(0xffffffffu, m1, 2));
            m0 *= SCL2; m1 *= SCL2;
            if (!first) {
              m0 = fmaxf(m0, f0); m1 = fmaxf(m1, f1);
              const float c0 = ex2(f0 - m0), c1 = ex2(f1 - m1);
              l0 *= c0; l1 *= c1;
              wg_wait<0>();
              keep(o);
#pragma unroll
              for (int i = 0; i < 16; i++) { o[4 * i] *= c0; o[4 * i + 1] *= c0; o[4 * i + 2] *= c1; o[4 * i + 3] *= c1; }
            }
            f0 = m0; f1 = m1;
          }
          float b0 = 0.f, b1 = 0.f;
          a0 = 0.f; a1 = 0.f;
#pragma unroll
          for (int i = 0; i < 16; i++) {
            const float e0 = ex2(fmaf(s[4 * i], SCL2, -f0)), e1 = ex2(fmaf(s[4 * i + 1], SCL2, -f0));
            const float e2 = ex2(fmaf(s[4 * i + 2], SCL2, -f1)), e3 = ex2(fmaf(s[4 * i + 3], SCL2, -f1));
            a0 += e0; b0 += e1; a1 += e2; b1 += e3;
            pw[2 * i] = pack_bf(e0, e1); pw[2 * i + 1] = pack_bf(e2, e3);
            if (i == VREL) {
#pragma unroll
              for (int k = 0; k < 2 * VREL + 2; k++) asm volatile("" : "+r"(pw[k])::"memory");
              mbar_wait(bfull + (ODD ? 24 : 8), ph);
              wg_wait<0>();
              mbar_arrive_cl(rempty, ODD ? 16 : (j ? 0 : GE + 16), !again);
              if (!ODD) mbar_arrive_cl(rempty, GE + 24, !again && j == 0);
#pragma unroll
              for (int k = 4 * VREL + 4; k < 64; k++) asm volatile("" : "+f"(s[k])::"memory");
            }
          }
          a0 += b0; a1 += b1;
          if (redo) break;
          redo = __any_sync(0xffffffffu, !(a0 + a1 < 0x1p70f));
          if (first) {
            uint32_t m0 = __ballot_sync(0xffffffffu, a0 > 0x1p-50f), m1 = __ballot_sync(0xffffffffu, a1 > 0x1p-50f);
            m0 |= m0 >> 1; m1 |= m1 >> 1; m0 |= m0 >> 2; m1 |= m1 >> 2;
            redo = redo || (m0 & m1 & 0x11111111u) != 0x11111111u;
          }
          if (!redo) break;
          again = true;
        }
        l0 += a0; l1 += a1;
        keep(pw);
        keep(o);
        const uint32_t qo = qt >> (j ? 0 : 8);
        if (first) store_chunk<0>(o, i0, i1, qw + unit_of(qo, 0) + frag_offset(warp));
        keep(o);
        bar_sync(2 + wg, 256);
        if (!last) {
          const uint32_t qn = qt >> (j >= 3 ? 8 : 0);
          wg_fence();
          issue_qk(s, qw + unit_of(qn, 0), qw + unit_of(qn, 1), base + unit_of(at, ODD ? 3 : 1));
          wg_commit();
          mbar_wait(bfull + (ODD ? 0 : 16), ODD ? ph ^ 1 : ph);
        }
        if (first) { store_chunk<1>(o, i0, i1, qw + unit_of(qo, 1) + frag_offset(warp)); keep(o); }
        wg_fence();
        issue_pv(o, pw, base + unit_of(at, ODD ? (last ? 3 : 0) : 2), !first);
        wg_commit();
        bar_arrive(3 - wg, 256);
        if (first) { fence_async_smem(); mbar_arrive_pred(bar_ofull + wg * 8, j); PROF(2, tid == 0 && j, 9 + ps * 8); }
        wg_wait<1>();
        keep(s);
        mbar_arrive_cl(rempty, ODD ? 24 : 8, !last);
        PROF(4, tid == 0 && ps == 1, 51 + j);
      };
      uint32_t pa[32], pb[32];
#pragma unroll 1
      for (int j = 0; j < 8; j += 2) {
        step(std::false_type{}, j, pa, pb);
        step(std::true_type{}, j + 1, pb, pa);
      }
      {
        const float i0 = inv_quad_sum(l0), i1 = inv_quad_sum(l1);
        wg_wait<0>();
        keep(o);
        mbar_arrive_cl(rempty, 24);
        store_chunk<0>(o, i0, i1, qw + unit_of(qt, 2) + frag_offset(warp));
        store_chunk<1>(o, i0, i1, qw + unit_of(qt, 3) + frag_offset(warp));
        fence_async_smem();
        mbar_arrive(bar_ofull + wg * 8);
      }
      PROF(2, tid == 0, 10 + ps * 8);
    }

    const int ln = fresh_lane(), g = ln >> 2, tq = ln & 3, ct = warp * 32 + ln;
    const bool lane0 = ln == 0;
    const int lrow0 = warp * 16 + g;
    const int grow0 = rb * 128 + lrow0;
    const uint32_t res = base + OFF_RES, trow = res + wg * 8192 + frag_offset(warp);
    uint32_t xr[32];
    {
      const uint64_t da = make_desc(base + wg * 8192, 16, 1024), db = make_desc(base, 8192, 1024);
      constexpr int U = UNIT / 16;
#define HALF_STAGE(acc, xu, wu) _Pragma("unroll") for (int kk = 0; kk < 4; kk++) mma_ss<1>(acc, da + (xu) * U + kk * 2, db + (wu) * U + kk * 128, 1)
      PROF(10, ct == PT, 19); STAMP(0);
      cluster_arrive();
      mbar_wait(gfull, 1);
      mbar_wait(gfull + 8, 1);
      bar_sync(2 + wg, 256);
      wg_fence();
      HALF_STAGE(o, 6, 8);
      HALF_STAGE(o, 9, 11);
      wg_commit();
      STAMP(16);
      mbar_wait(gfull + 16, 1);
      STAMP(17);
      wg_fence();
      HALF_STAGE(o, 12, 1);
      wg_commit();
      bar_arrive(3 - wg, 256);
      mbar_wait(bar_par, 0);
      uint32_t* xo = g_xch + ((size_t)b * 8 * 256 + ct) * 4;
      const uint32_t* xi = g_xch + ((size_t)(b ^ 2) * 8 * 256 + ct) * 4;
      const uint32_t par1 = (~lds1(par + PAR_CONST + 4) & 1) << 16;
      wg_wait<0>();
      keep(o);
      mbar_arrive_pred(bar_ring, lane0);
      PROF(8, ct == PT, 20); STAMP(1);
#define SEND(i) st_b128(xo + (i) * 1024, (pack_bf(o[8 * (i)], o[8 * (i) + 1]) & ~0x10000u) | par1, pack_bf(o[8 * (i) + 2], o[8 * (i) + 3]), \
                        pack_bf(o[8 * (i) + 4], o[8 * (i) + 5]), pack_bf(o[8 * (i) + 6], o[8 * (i) + 7]))
#pragma unroll
      for (int i = 0; i < NS1; i++) SEND(i);
      PROF(8, ct == PT, 21); STAMP(2);
      bar_sync(2 + wg, 256);
      wg_fence();
      HALF_STAGE(s, 6, 7);
      HALF_STAGE(s, 9, 10);
      HALF_STAGE(s, 12, 0);
      wg_commit();
      bar_arrive(3 - wg, 256);
      STAMP(18);
      mbar_wait(gfull + 24, 1);
#pragma unroll
      for (int i = NS1; i < 8; i++) SEND(i);
      uint4 v[8];
#pragma unroll
      for (int i = 0; i < 4; i++) v[i] = ld_b128(xi + i * 1024);
      STAMP(19);
      mbar_wait(bar_rx, 0);
      wg_wait<0>();
      mbar_arrive_pred(bar_ring + 8, lane0);
      bar_sync(2 + wg, 256);
      STAMP(20);
#pragma unroll
      for (int i = 4; i < 8; i++) v[i] = ld_b128(xi + i * 1024);
      mbar_wait(bar_xres, 0);
      wg_fence();
      HALF_STAGE(s, 13, 2);
      HALF_STAGE(s, 8, 3);
      wg_commit();
      bar_arrive(3 - wg, 256);
      STAMP(21);
      wg_wait<0>();
      keep(s);
      mbar_arrive_pred(bar_ring + 16, lane0);
      PROF(10, ct == PT, 23); STAMP(4);
#pragma unroll
      for (int i = 0; i < 16; i += 2) ldmatrix4((trow ^ ((i & 7) << 4)) + (i >> 3) * 16384, xr[2 * i], xr[2 * i + 1], xr[2 * i + 2], xr[2 * i + 3]);
      {
        uint32_t n = 0;
        bool ok;
        do {
          ok = true;
#pragma unroll
          for (int i = 0; i < 8; i++)
            if ((v[i].x & 0x10000u) != par1) { v[i] = ld_b128(xi + i * 1024); ok = false; }
          watchdog(n);
        } while (!ok);
      }
      __syncwarp();
      PROF(8, ct == PT, 22); STAMP(3);
      float ds[4] = {0.f, 0.f, 0.f, 0.f}, dl[4] = {0.f, 0.f, 0.f, 0.f}, q0[4] = {0.f, 0.f, 0.f, 0.f}, q1[4] = {0.f, 0.f, 0.f, 0.f};
#pragma unroll
      for (int i = 0; i < 8; i++) {
        const uint32_t ga0 = lds1(par + PAR_T2 + i * 128 + tq * 16 + 12), ga1 = lds1(par + PAR_T2 + i * 128 + 64 + tq * 16 + 12);
        const uint4 bw = lds4(par + PAR_T1 + i * 64 + tq * 16);
        const uint32_t u0 = hfma2(ga0, hadd2(pack_bf(s[8 * i], s[8 * i + 1]), v[i].x & ~0x10000u), xr[4 * i]);
        const uint32_t u1 = hfma2(ga0, hadd2(pack_bf(s[8 * i + 2], s[8 * i + 3]), v[i].y), xr[4 * i + 1]);
        const uint32_t u2 = hfma2(ga1, hadd2(pack_bf(s[8 * i + 4], s[8 * i + 5]), v[i].z), xr[4 * i + 2]);
        const uint32_t u3 = hfma2(ga1, hadd2(pack_bf(s[8 * i + 6], s[8 * i + 7]), v[i].w), xr[4 * i + 3]);
        xr[4 * i] = u0; xr[4 * i + 1] = u1; xr[4 * i + 2] = u2; xr[4 * i + 3] = u3;
        mma16816(ds, u0, u1, u2, u3, (g & 1) ? bw.x : 0x3f803f80u, (g & 1) ? bw.y : 0x3f803f80u);
        mma16816(dl, u0, u1, u2, u3, bw.z, bw.w);
        mma16816(q0, u0, u1, u2, u3, u0, u2);
        mma16816(q1, u0, u1, u2, u3, u1, u3);
      }
      if (tq == (g >> 1)) {
        uint32_t* dst = g_stats + ((size_t)cj * SEQ + grow0) * 4;
        st_b128(dst, __float_as_uint(ds[0]), __float_as_uint((g & 1) ? q0[1] : q0[0]), __float_as_uint(ds[1] + dl[1]), tag);
        st_b128(dst + 32, __float_as_uint(ds[2]), __float_as_uint((g & 1) ? q1[3] : q1[2]), __float_as_uint(ds[3] + dl[3]), tag);
      }
    }
    PROF(8, ct == PT, 29); STAMP(5);
    uint32_t mm, ih, il;
    float rbest;
    uint32_t wf[128];
    const uint32_t frow = (ln & 7) + (ln >> 4) * 8;
    const uint32_t wfo = base + (warp & 1) * 8192 + frow * 64 + ((((ln >> 3) & 1) ^ ((frow >> 1) & 3)) << 4);
#define LOAD_WF(m) _Pragma("unroll") for (int f = 0; f < 16; f++) {                                                   \
      const int r = ((f >> 1) * 4 + (m) * 2 + (f & 1)) * 4;                                                           \
      ldmatrix4t(((wfo + unit_of((m) ? FT_U : FT_G, warp >> 1)) ^ ((f & 1) * 32)) + (f >> 1) * 1024, wf[r], wf[r + 1], wf[r + 2], wf[r + 3]); \
    }
    bool early;
    {
      const uint32_t* sp = g_stats + ((size_t)(tq >> 1) * 4 * SEQ + grow0 + (tq & 1) * 8) * 4;
      uint4 v0 = ld_b128(sp), v1 = ld_b128(sp + SEQ * 4), v2 = ld_b128(sp + SEQ * 8), v3 = ld_b128(sp + SEQ * 12);
#pragma unroll
      for (int i = 0; i < 16; i += 2) stmatrix4((trow ^ ((i & 7) << 4)) + (i >> 3) * 16384, xr[2 * i], xr[2 * i + 1], xr[2 * i + 2], xr[2 * i + 3]);
      early = __all_sync(0xffffffffu, b >= NFFN || mbar_test(bar_box + (warp >> 1) * 8, 0));
      LOAD_WF(0);
      __syncwarp();
      mbar_arrive_pred(bar_gate, lane0 && early);
      const uint4 cst = lds4(par + PAR_CONST);
      const float A1 = __uint_as_float(cst.x), A2 = __uint_as_float(cst.z);
      uint32_t n = 0;
      while (v0.w != tag || v1.w != tag || v2.w != tag || v3.w != tag) {
        if (v0.w != tag) v0 = ld_b128(sp);
        if (v1.w != tag) v1 = ld_b128(sp + SEQ * 4);
        if (v2.w != tag) v2 = ld_b128(sp + SEQ * 8);
        if (v3.w != tag) v3 = ld_b128(sp + SEQ * 12);
        watchdog(n);
      }
      __syncwarp();
      PROF(8, ct == PT, 30); STAMP(6);
      float su = (__uint_as_float(v0.x) + __uint_as_float(v1.x)) + (__uint_as_float(v2.x) + __uint_as_float(v3.x));
      float sq = (__uint_as_float(v0.y) + __uint_as_float(v1.y)) + (__uint_as_float(v2.y) + __uint_as_float(v3.y));
      float dt = (__uint_as_float(v0.z) + __uint_as_float(v1.z)) + (__uint_as_float(v2.z) + __uint_as_float(v3.z));
      su += __shfl_xor_sync(0xffffffffu, su, 2); sq += __shfl_xor_sync(0xffffffffu, sq, 2); dt += __shfl_xor_sync(0xffffffffu, dt, 2);
      const float m = su * (1.f / DM);
      float mb, sd;
      ln_scalars(m, fmaxf(sq * (1.f / DM) - m * m, 0.f), mb, sd);
      const float inv = rcp(sd);
      rbest = (dt - mb * A1) * inv + A2;
      mm = pack_bf(mb, mb);
      ih = pack_bf(inv, inv);
      const float lo = inv - bf_lo(ih);
      il = pack_bf(lo, lo);
    }
    int ibest;
    {
      const uint32_t bits = __float_as_uint(rbest);
      const uint32_t key = (((int)bits < 0 ? ~bits : bits | 0x80000000u) & ~0x1ffu) | ((127 - lrow0 - (tq & 1) * 8) << 2) | tag;
      sts1(par + PAR_RED + warp * 4, __reduce_max_sync(0xffffffffu, key));
      PROF(8, ct == PT, 38); STAMP(7);
      bar_sync(1, 256);
      const uint4 ka = lds4(par + PAR_RED), kb = lds4(par + PAR_RED + 16);
      const uint32_t k2 = max(max(max(ka.x, ka.y), max(ka.z, ka.w)), max(max(kb.x, kb.y), max(kb.z, kb.w)));
      if (ct < 16) st_relaxed(g_cand + (cj * 16 + ct) * 32 + rb, k2);
      ibest = 127 - ((k2 >> 2) & 127);
    }
    PROF(8, ct == PT, 39); STAMP(8);
    if ((ibest >> 4) == warp) {
      const int src = (ibest & 7) * 4 + ((ibest >> 3) & 1), ch = g * 2;
      const uint32_t cm = __shfl_sync(0xffffffffu, mm, src), ch_ = __shfl_sync(0xffffffffu, ih, src), cl = __shfl_sync(0xffffffffu, il, src);
      const uint32_t xa = res + (ch >> 3) * 16384 + ibest * 128 + (((ch & 7) ^ (ibest & 7)) << 4) + tq * 4;
      const uint32_t x0 = lds1(xa), x1 = lds1(xa ^ 16);
      const uint2 p0 = lds2(par + PAR_T2 + ch * 64 + tq * 16), p1 = lds2(par + PAR_T2 + ch * 64 + 64 + tq * 16);
      uint32_t* dst = g_row + rb * 2 * DM + cj * 128 + ln * 4;
      st_pairs(dst, ln_mod(x0, cm, ch_, cl, p0.x, p0.y), ln_mod(x1, cm, ch_, cl, p1.x, p1.y), tag);
      st_pairs(dst + DM, x0, x1, tag);
      __syncwarp();
    }
    PROF(8, ct == PT, 37); STAMP(9);
    uint32_t wd[64];
    const uint32_t wda = base + unit_of(FT_D, warp >> 1) + (warp & 1) * 8192 + frow * 128 + ((((ln >> 3) & 1) ^ (ln & 7)) << 4);
#define LOAD_WD(f) ldmatrix4t((wda ^ ((((f) >> 1) & 3) * 32)) + ((f) >> 3) * 4096 + ((f) & 1) * 2048, wd[4 * (f)], wd[4 * (f) + 1], wd[4 * (f) + 2], wd[4 * (f) + 3])
    if (!early) {
      mbar_wait(bar_box + (warp >> 1) * 8, 0);
      LOAD_WF(0);
      __syncwarp();
      mbar_arrive_pred(bar_gate, lane0);
    }
    if (b < NFFN) {
      const uint32_t own = base + unit_of(FT_G, warp >> 1) + (warp & 1) * 8192;
      mbar_wait(bar_box + (4 + (warp >> 1)) * 8, 0);
      LOAD_WF(1);
      uint32_t* const ydst = g_ypart + ((size_t)(warp * 16 + tq * 2) * NFFN + b) * 8 + g;
      PROF(8, ct == PT, 31); STAMP(10);
      mbar_wait(bar_sel, 0);
      PROF(8, ct == PT, 33); STAMP(12);
      float d[8][4];
#pragma unroll
      for (int i = 0; i < 8; i++) { d[i][0] = 0.f; d[i][1] = 0.f; d[i][2] = 0.f; d[i][3] = 0.f; }
#pragma unroll
      for (int ks = 0; ks < 8; ks++) {
        const uint2 hb = lds2(own + 256 + ks * 32 + tq * 8);
#pragma unroll
        for (int mt = 0; mt < 4; mt++) {
          const int r = ks * 16 + mt * 4;
          mma16816(d[mt + (ks & 1) * 4], wf[r], wf[r + 1], wf[r + 2], wf[r + 3], hb.x, hb.y);
        }
      }
      if (tq == 0) {
        const uint32_t dst = own + g * 32;
        sts4(dst, make_uint4(__float_as_uint(d[0][0] + d[4][0]), __float_as_uint(d[0][2] + d[4][2]), __float_as_uint(d[1][0] + d[5][0]), __float_as_uint(d[1][2] + d[5][2])));
        sts4(dst + 16, make_uint4(__float_as_uint(d[2][0] + d[6][0]), __float_as_uint(d[2][2] + d[6][2]), __float_as_uint(d[3][0] + d[7][0]), __float_as_uint(d[3][2] + d[7][2])));
      }
      mbar_wait(bar_box + (8 + (warp >> 1)) * 8, 0);
#pragma unroll
      for (int f = 0; f < WDE; f++) LOAD_WD(f);
      bar_sync(1, 256);
      uint32_t ab[4];
      {
        float G = 0.f, U = 0.f;
        const uint32_t src = base + (ln & 7) * 32 + (ln >> 3) * 4;
#pragma unroll
        for (int w8 = 0; w8 < 8; w8++) {
          const uint32_t a = src + ((FT_G >> (w8 >> 1) * 4) & 15) * UNIT + (w8 & 1) * 8192;
          G += __uint_as_float(lds1(a)); U += __uint_as_float(lds1(a + 16));
        }
#pragma unroll
        for (int f = WDE; f < 16; f++) LOAD_WD(f);
        const float act = rbf(silu_f(rbf(G))) * rbf(U);
        const uint32_t pk = pack_bf(act, __shfl_down_sync(0xffffffffu, act, 1));
#pragma unroll
        for (int i = 0; i < 4; i++) ab[i] = __shfl_sync(0xffffffffu, pk, i * 8 + tq * 2);
      }
      PROF(8, ct == PT, 34); STAMP(13);
#pragma unroll
      for (int mt = 0; mt < 8; mt++) {
        d[mt][0] = 0.f; d[mt][1] = 0.f; d[mt][2] = 0.f; d[mt][3] = 0.f;
        mma16816(d[mt], wd[mt * 8], wd[mt * 8 + 1], wd[mt * 8 + 2], wd[mt * 8 + 3], ab[0], ab[1]);
        mma16816(d[mt], wd[mt * 8 + 4], wd[mt * 8 + 5], wd[mt * 8 + 6], wd[mt * 8 + 7], ab[2], ab[3]);
      }
#pragma unroll
      for (int i = 0; i < 4; i++) {
        const int m4 = (i >> 1) * 4, e = (i & 1) * 2;
        const float y = (tq & 2) ? ((tq & 1) ? d[m4 + 3][e] : d[m4 + 2][e]) : ((tq & 1) ? d[m4 + 1][e] : d[m4][e]);
        st_relaxed(ydst + (m4 * 2 + (i & 1)) * NFFN * 8, tagf(y, tag));
      }
      PROF(8, ct == PT, 35); STAMP(14);
    }
    mbar_wait(bar_sel, 0);
    mbar_arrive_pred(bar_win, ct == 0);
    const int iwin = lds1(par + PAR_CONST + 60) & 0x7ff;
    {
      const uint32_t mm0 = __shfl_sync(0xffffffffu, mm, ln & ~1), mm1 = __shfl_sync(0xffffffffu, mm, ln | 1);
      const uint32_t ih0 = __shfl_sync(0xffffffffu, ih, ln & ~1), ih1 = __shfl_sync(0xffffffffu, ih, ln | 1);
      const uint32_t il0 = __shfl_sync(0xffffffffu, il, ln & ~1), il1 = __shfl_sync(0xffffffffu, il, ln | 1);
      const bool mine = (iwin >> 4) == rb * 8 + warp;
#pragma unroll 1
      for (int hf = 0; hf < 2; hf++) {
        uint32_t x[16];
#pragma unroll
        for (int i = 0; i < 8; i += 2) ldmatrix4((trow ^ (i << 4)) + hf * 16384, x[2 * i], x[2 * i + 1], x[2 * i + 2], x[2 * i + 3]);
#pragma unroll
        for (int i = 0; i < 8; i++) {
          const uint4 pv = lds4(par + PAR_T2 + (hf * 8 + i) * 64 + tq * 16);
          x[2 * i] = hadd2(x[2 * i], hmul2(pv.z, ln_mod(x[2 * i], mm0, ih0, il0, pv.x, pv.y)));
          x[2 * i + 1] = hadd2(x[2 * i + 1], hmul2(pv.z, ln_mod(x[2 * i + 1], mm1, ih1, il1, pv.x, pv.y)));
        }
        if (mine) {
          uint32_t* dst = reinterpret_cast<uint32_t*>(P.out + (size_t)grow0 * DM + cj * 128 + hf * 64) + tq;
#pragma unroll
          for (int i = 0; i < 8; i++) {
            if (grow0 != iwin) dst[i * 4] = x[2 * i];
            if (grow0 + 8 != iwin) dst[i * 4 + 4 * DM] = x[2 * i + 1];
          }
        } else {
#pragma unroll
          for (int i = 0; i < 8; i += 2) stmatrix4((trow ^ (i << 4)) + hf * 16384, x[2 * i], x[2 * i + 1], x[2 * i + 2], x[2 * i + 3]);
          fence_async_smem();
          __syncwarp();
          if (elect_one()) {
            tma2d_store(&maps.out, res + hf * 16384 + warp * 2048, cj * 128 + hf * 64, rb * 128 + warp * 16);
            asm volatile("cp.async.bulk.commit_group;" ::: "memory");
          }
        }
      }
      asm volatile("cp.async.bulk.wait_group.read 0;" ::: "memory");
    }
    PROF(8, ct == PT, 11); STAMP(15);
    cluster_wait();
  }
}

typedef CUresult (*EncodeFn)(CUtensorMap*, CUtensorMapDataType, cuuint32_t, void*, const cuuint64_t*, const cuuint64_t*,
                             const cuuint32_t*, const cuuint32_t*, CUtensorMapInterleave, CUtensorMapSwizzle,
                             CUtensorMapL2promotion, CUtensorMapFloatOOBfill);

void map2d(EncodeFn enc, CUtensorMap* m, const void* p, uint64_t rows, uint64_t cols, uint32_t brows) {
  cuuint64_t dims[2] = {cols, rows}, strides[1] = {cols * 2};
  cuuint32_t box[2] = {64, brows}, es[2] = {1, 1};
  enc(m, CU_TENSOR_MAP_DATA_TYPE_BFLOAT16, 2, const_cast<void*>(p), dims, strides, box, es, CU_TENSOR_MAP_INTERLEAVE_NONE,
      CU_TENSOR_MAP_SWIZZLE_128B, CU_TENSOR_MAP_L2_PROMOTION_L2_256B, CU_TENSOR_MAP_FLOAT_OOB_FILL_NONE);
}
void map2d_narrow(EncodeFn enc, CUtensorMap* m, const void* p, uint64_t rows, uint64_t cols) {
  cuuint64_t dims[2] = {cols, rows}, strides[1] = {cols * 2};
  cuuint32_t box[2] = {32, 256}, es[2] = {1, 1};
  enc(m, CU_TENSOR_MAP_DATA_TYPE_BFLOAT16, 2, const_cast<void*>(p), dims, strides, box, es, CU_TENSOR_MAP_INTERLEAVE_NONE,
      CU_TENSOR_MAP_SWIZZLE_64B, CU_TENSOR_MAP_L2_PROMOTION_L2_64B, CU_TENSOR_MAP_FLOAT_OOB_FILL_NONE);
}
void map3d(EncodeFn enc, CUtensorMap* m, const void* p, uint64_t rows, uint64_t cols, uint32_t brows, uint32_t nch) {
  cuuint64_t dims[3] = {64, rows, cols / 64}, strides[2] = {cols * 2, 128};
  cuuint32_t box[3] = {64, brows, nch}, es[3] = {1, 1, 1};
  enc(m, CU_TENSOR_MAP_DATA_TYPE_BFLOAT16, 3, const_cast<void*>(p), dims, strides, box, es, CU_TENSOR_MAP_INTERLEAVE_NONE,
      CU_TENSOR_MAP_SWIZZLE_128B, CU_TENSOR_MAP_L2_PROMOTION_L2_256B, CU_TENSOR_MAP_FLOAT_OOB_FILL_NONE);
}

}

extern "C" void kernel_launch(void* const* d_in, const int* in_sizes, int n_in, void* d_out, int out_size) {
  (void)in_sizes; (void)n_in; (void)out_size;
  static EncodeFn enc = nullptr;
  if (!enc) {
    void* fn = nullptr;
    cudaDriverEntryPointQueryResult st;
    cudaGetDriverEntryPoint("cuTensorMapEncodeTiled", &fn, cudaEnableDefault, &st);
    enc = (EncodeFn)fn;
    cudaFuncSetAttribute(fused_kernel, cudaFuncAttributeMaxDynamicSharedMemorySize, SMEM_BYTES);
  }
  Maps maps;
  map2d(enc, &maps.x, d_in[0], SEQ, DM, 128);
  map2d(enc, &maps.out, d_out, SEQ, DM, 16);
  map3d(enc, &maps.wq, d_in[3], DM, NQ, 64, 2);
  map3d(enc, &maps.k, d_in[1], 4 * SK, 128, 128, 1);
  map3d(enc, &maps.v, d_in[2], 4 * SK, 128, 128, 1);
  map3d(enc, &maps.wo, d_in[4], NQ, DM, 64, 2);
  map2d_narrow(enc, &maps.wg, d_in[7], DM, FF);
  map2d_narrow(enc, &maps.wu, d_in[8], DM, FF);
  map3d(enc, &maps.wd, d_in[9], FF, DM, 32, 4);
  map2d_narrow(enc, &maps.wm, d_in[11], DM, NMOD);
  Ptrs p;
  p.x = (const __nv_bfloat16*)d_in[0];
  p.w_r = (const __nv_bfloat16*)d_in[6];
  p.w_gate = (const __nv_bfloat16*)d_in[7];
  p.w_up = (const __nv_bfloat16*)d_in[8];
  p.w_down = (const __nv_bfloat16*)d_in[9];
  p.c = (const __nv_bfloat16*)d_in[10];
  p.w_mod = (const __nv_bfloat16*)d_in[11];
  p.out = (__nv_bfloat16*)d_out;
  fused_kernel<<<NMAIN + NHELP, 384, SMEM_BYTES>>>(maps, p);
}
```

```cpp
#include <cuda_runtime.h>
#include <cuda_bf16.h>
#include <cuda.h>
#include <stdint.h>
#include <type_traits>

#define HD 1
#define HDX 2
#define XF 4
#define XE 32
#define XR 0
#define PF2 1
#define PF2T 4
#define NRS 6
#define FPACE 3
#define GOST 20
#define WB 2
#define WN 24
#define RES0 17
#define RES1 20
#define HU 32
#define NS1 6
#define PD0 40
#define PG0 31
#define PSL 120
#define WDE 16
#define VREL 7
#define E0 3

namespace {

constexpr int SEQ = 2048, DM = 1024, NQ = 4096, SK = 2048, WIN = 512, FF = 3584, NMOD = 6144;
constexpr int NMAIN = 128, NHELP = 4, NFFN = 112;
constexpr int NSLOT = 4, SLOT_BYTES = 32768, UNIT = 16384, GST_BYTES = 3 * UNIT;
constexpr uint32_t XT0 = 0x9630, XT1 = 0x54DC, XT2 = 0xDC96;
constexpr uint32_t WT0 = 0xA741, WT1 = 0x720A, WT2 = 0x20A7;
constexpr uint32_t AT0 = 0x7420, AT1 = 0x2C0A;
constexpr uint32_t QT = 0x549696DC;
constexpr int OFF_STAGE = 12 * UNIT;
constexpr uint32_t FT_G = 0x761B, FT_U = 0x0CA9, FT_D = 0x382D;
constexpr int OFF_RES = 4 * UNIT;
constexpr int OFF_PAR = 14 * UNIT;
constexpr int OFF_BAR = OFF_PAR + 2048 + 512;
constexpr int SMEM_BYTES = OFF_BAR + 512;
static_assert(SMEM_BYTES <= 232448, "smem");

constexpr int PAR_T1 = 0;
constexpr int PAR_T2 = 512;
constexpr int PAR_CONST = 1536;
constexpr int PAR_RED = 1600;
constexpr int PAR_SINK = 2176;

struct Maps {
  CUtensorMap x, wq, k, v, wo, wg, wu, wd, wm, out;
};
struct Ptrs {
  const __nv_bfloat16 *x, *w_r, *c, *w_mod, *w_gate, *w_up, *w_down;
  __nv_bfloat16* out;
};

__device__ __align__(1024) uint8_t g_act[16 * 80 * UNIT];
__device__ __align__(128) uint32_t g_mod[NMOD];
__device__ __align__(128) uint32_t g_modp[2 * 2 * DM];
__device__ __align__(128) uint32_t g_ln1[SEQ * 4];
__device__ __align__(128) uint32_t g_cnt_h[16 * 32];
__device__ __align__(128) uint32_t g_cnt_o[128 * 32];
__device__ __align__(128) uint32_t g_xch[NMAIN * 8 * 256 * 4];
__device__ __align__(128) uint32_t g_stats[8 * SEQ * 4];
__device__ __align__(128) uint32_t g_cand[NMAIN * 32];
__device__ __align__(128) uint32_t g_row[16 * 2 * DM];
__device__ __align__(128) uint32_t g_ypart[NMAIN * NFFN * 8];
__device__ uint32_t g_epoch;

__device__ __forceinline__ uint32_t fresh_lane() { uint32_t l; asm volatile("mov.u32 %0, %%laneid;" : "=r"(l)); return l; }
__device__ __forceinline__ uint32_t frag_offset(int warp) {
  const uint32_t l = fresh_lane();
  return ((warp & 3) * 16 + (l & 15)) * 128 + (((l >> 4) ^ (l & 7)) << 4);
}
__device__ __forceinline__ bool elect_one() {
  uint32_t p;
  asm volatile("{ .reg .pred q; elect.sync _|q, 0xffffffff; selp.u32 %0, 1, 0, q; }" : "=r"(p));
  return p;
}
__device__ __forceinline__ uint32_t smem_u32(const void* p) { return (uint32_t)__cvta_generic_to_shared(p); }
__device__ __forceinline__ void mbar_init(uint32_t bar, uint32_t cnt) {
  asm volatile("mbarrier.init.shared::cta.b64 [%0], %1;" ::"r"(bar), "r"(cnt) : "memory");
}
__device__ __forceinline__ void mbar_expect_tx(uint32_t bar, uint32_t bytes) {
  asm volatile("mbarrier.arrive.expect_tx.shared::cta.b64 _, [%0], %1;" ::"r"(bar), "r"(bytes) : "memory");
}
__device__ __forceinline__ void mbar_arrive(uint32_t bar) {
  asm volatile("mbarrier.arrive.shared::cta.b64 _, [%0];" ::"r"(bar) : "memory");
}
__device__ __forceinline__ void mbar_arrive_pred(uint32_t bar, bool p) {
  asm volatile("{ .reg .pred p; setp.ne.b32 p, %1, 0; @p mbarrier.arrive.shared::cta.b64 _, [%0]; }" ::"r"(bar), "r"((int)p) : "memory");
}
__device__ __forceinline__ void mbar_arrive_cl(uint32_t bar, uint32_t off, bool p = true) {
  asm volatile("{ .reg .pred p, q; .reg .b32 a; setp.ne.b32 q, %2, 0; setp.ne.and.b32 p, %0, 0, q; add.u32 a, %0, %1; @p mbarrier.arrive.shared::cluster.b64 _, [a]; }"
               ::"r"(bar), "r"(off), "r"((int)p) : "memory");
}
__device__ __forceinline__ uint32_t mapa(uint32_t addr, uint32_t cta) {
  uint32_t r; asm("mapa.shared::cluster.u32 %0, %1, %2;" : "=r"(r) : "r"(addr), "r"(cta)); return r;
}
__device__ __forceinline__ void cluster_arrive() { asm volatile("barrier.cluster.arrive.relaxed.aligned;" ::: "memory"); }
__device__ __forceinline__ void cluster_wait() { asm volatile("barrier.cluster.wait.aligned;" ::: "memory"); }
__device__ __forceinline__ void watchdog(uint32_t& n) {
}
__device__ __forceinline__ void mbar_wait(uint32_t bar, uint32_t parity) {
  asm volatile("{\n.reg .pred p;\nWAIT_%=:\nmbarrier.try_wait.parity.shared::cta.b64 p, [%0], %1;\n@!p bra WAIT_%=;\n}" ::"r"(bar), "r"(parity) : "memory");
}
__device__ __forceinline__ bool mbar_test(uint32_t bar, uint32_t parity) {
  uint32_t ok;
  asm volatile("{\n.reg .pred p;\nmbarrier.test_wait.parity.shared::cta.b64 p, [%1], %2;\nselp.u32 %0, 1, 0, p;\n}" : "=r"(ok) : "r"(bar), "r"(parity) : "memory");
  return ok;
}
__device__ __forceinline__ uint64_t l2_stream() {
  uint64_t f; asm("createpolicy.fractional.L2::evict_first.b64 %0, 1.0;" : "=l"(f)); return f;
}
__device__ __forceinline__ void tma2d(uint32_t dst, const CUtensorMap* m, int c0, int c1, uint32_t bar) {
  asm volatile("cp.async.bulk.tensor.2d.shared::cluster.global.mbarrier::complete_tx::bytes.L2::cache_hint [%0], [%1, {%3, %4}], [%2], %5;"
               ::"r"(dst), "l"(m), "r"(bar), "r"(c0), "r"(c1), "l"(l2_stream()) : "memory");
}
__device__ __forceinline__ void tma3d_prefetch(const CUtensorMap* m, int c0, int c1, int c2) {
  asm volatile("cp.async.bulk.prefetch.tensor.3d.L2.global.tile [%0, {%1, %2, %3}];" ::"l"(m), "r"(c0), "r"(c1), "r"(c2) : "memory");
}
__device__ __forceinline__ void bulk_load(uint32_t dst, const void* src, uint32_t bytes, uint32_t bar) {
  asm volatile("cp.async.bulk.shared::cluster.global.mbarrier::complete_tx::bytes [%0], [%1], %2, [%3];" ::"r"(dst), "l"(src), "r"(bytes), "r"(bar) : "memory");
}
__device__ __forceinline__ void bulk_load_stream(uint32_t dst, const void* src, uint32_t bytes, uint32_t bar) {
  asm volatile("cp.async.bulk.shared::cluster.global.mbarrier::complete_tx::bytes.L2::cache_hint [%0], [%1], %2, [%3], %4;"
               ::"r"(dst), "l"(src), "r"(bytes), "r"(bar), "l"(l2_stream()) : "memory");
}
__device__ __forceinline__ void tma2d_store(const CUtensorMap* m, uint32_t src, int c0, int c1) {
  asm volatile("cp.async.bulk.tensor.2d.global.shared::cta.bulk_group [%0, {%2, %3}], [%1];" ::"l"(m), "r"(src), "r"(c0), "r"(c1) : "memory");
}
__device__ __forceinline__ void bulk_store(void* dst, uint32_t src, uint32_t bytes) {
  asm volatile("cp.async.bulk.global.shared::cta.bulk_group [%0], [%1], %2;" ::"l"(dst), "r"(src), "r"(bytes) : "memory");
}
__device__ __forceinline__ uint32_t unit_of(uint32_t table, uint32_t i) { return ((table >> (i * 4)) & 15) * UNIT; }
__device__ __forceinline__ void tma3d(uint32_t dst, const CUtensorMap* m, int c0, int c1, int c2, uint32_t bar) {
  asm volatile("cp.async.bulk.tensor.3d.shared::cluster.global.mbarrier::complete_tx::bytes.L2::cache_hint [%0], [%1, {%3, %4, %5}], [%2], %6;"
               ::"r"(dst), "l"(m), "r"(bar), "r"(c0), "r"(c1), "r"(c2), "l"(l2_stream()) : "memory");
}
template <bool STREAM>
__device__ __forceinline__ void tma3d_mc(uint32_t dst, const CUtensorMap* m, int c0, int c1, int c2, uint32_t bar) {
  if (STREAM)
    asm volatile("cp.async.bulk.tensor.3d.shared::cluster.global.mbarrier::complete_tx::bytes.multicast::cluster.L2::cache_hint [%0], [%1, {%3, %4, %5}], [%2], %6, %7;"
                 ::"r"(dst), "l"(m), "r"(bar), "r"(c0), "r"(c1), "r"(c2), "h"((uint16_t)3), "l"(l2_stream()) : "memory");
  else
    asm volatile("cp.async.bulk.tensor.3d.shared::cluster.global.mbarrier::complete_tx::bytes.multicast::cluster [%0], [%1, {%3, %4, %5}], [%2], %6;"
                 ::"r"(dst), "l"(m), "r"(bar), "r"(c0), "r"(c1), "r"(c2), "h"((uint16_t)3) : "memory");
}
__device__ __forceinline__ void prefetch_map(const CUtensorMap* m) {
  asm volatile("prefetch.tensormap [%0];" ::"l"(m) : "memory");
}
__device__ __forceinline__ void fence_async() { asm volatile("fence.proxy.async.global;" ::: "memory"); }
__device__ __forceinline__ void fence_async_smem() { asm volatile("fence.proxy.async.shared::cta;" ::: "memory"); }
__device__ __forceinline__ void bar_sync(int id, int n) { asm volatile("bar.sync %0, %1;" ::"r"(id), "r"(n) : "memory"); }
__device__ __forceinline__ void bar_arrive(int id, int n) { asm volatile("bar.arrive %0, %1;" ::"r"(id), "r"(n) : "memory"); }
__device__ __forceinline__ void wg_fence() { asm volatile("wgmma.fence.sync.aligned;" ::: "memory"); }
__device__ __forceinline__ void wg_commit() { asm volatile("wgmma.commit_group.sync.aligned;" ::: "memory"); }
template <int N> __device__ __forceinline__ void wg_wait() { asm volatile("wgmma.wait_group.sync.aligned %0;" ::"n"(N) : "memory"); }
__device__ __forceinline__ uint64_t make_desc(uint32_t addr, uint32_t lbo, uint32_t sbo) {
  return (uint64_t)((addr & 0x3FFFF) >> 4) | ((uint64_t)(lbo >> 4) << 16) | ((uint64_t)(sbo >> 4) << 32) | (1ull << 62);
}
__device__ __forceinline__ uint32_t ld_relaxed(const uint32_t* p) {
  uint32_t v; asm volatile("ld.relaxed.gpu.global.u32 %0, [%1];" : "=r"(v) : "l"(p) : "memory"); return v;
}
__device__ __forceinline__ uint32_t ld_acquire(const uint32_t* p) {
  uint32_t v; asm volatile("ld.acquire.gpu.global.u32 %0, [%1];" : "=r"(v) : "l"(p) : "memory"); return v;
}
__device__ __forceinline__ uint4 ld_relaxed4(const uint32_t* p) {
  uint4 v; asm volatile("ld.relaxed.gpu.global.v4.u32 {%0,%1,%2,%3}, [%4];" : "=r"(v.x), "=r"(v.y), "=r"(v.z), "=r"(v.w) : "l"(p) : "memory"); return v;
}
__device__ __forceinline__ uint2 ld_relaxed2(const uint32_t* p) {
  uint2 v; asm volatile("ld.relaxed.gpu.global.v2.u32 {%0,%1}, [%2];" : "=r"(v.x), "=r"(v.y) : "l"(p) : "memory"); return v;
}
__device__ __forceinline__ void st_relaxed(uint32_t* p, uint32_t v) {
  asm volatile("st.relaxed.gpu.global.u32 [%0], %1;" ::"l"(p), "r"(v) : "memory");
}
__device__ __forceinline__ void st_relaxed2(uint32_t* p, uint32_t a, uint32_t b) {
  asm volatile("st.relaxed.gpu.global.v2.u32 [%0], {%1,%2};" ::"l"(p), "r"(a), "r"(b) : "memory");
}
__device__ __forceinline__ void st_relaxed4(uint32_t* p, uint32_t a, uint32_t b, uint32_t c, uint32_t d) {
  asm volatile("st.relaxed.gpu.global.v4.u32 [%0], {%1,%2,%3,%4};" ::"l"(p), "r"(a), "r"(b), "r"(c), "r"(d) : "memory");
}
__device__ __forceinline__ void st_b128(uint32_t* p, uint32_t a, uint32_t b, uint32_t c, uint32_t d) {
  asm volatile("{ .reg .b64 u, v; .reg .b128 w; mov.b64 u, {%1, %2}; mov.b64 v, {%3, %4}; mov.b128 w, {u, v}; st.relaxed.gpu.global.b128 [%0], w; }"
               ::"l"(p), "r"(a), "r"(b), "r"(c), "r"(d) : "memory");
}
__device__ __forceinline__ uint4 ld_b128(const uint32_t* p) {
  uint4 r;
  asm volatile("{ .reg .b64 u, v; .reg .b128 w; ld.relaxed.gpu.global.b128 w, [%4]; mov.b128 {u, v}, w; mov.b64 {%0, %1}, u; mov.b64 {%2, %3}, v; }"
               : "=r"(r.x), "=r"(r.y), "=r"(r.z), "=r"(r.w) : "l"(p) : "memory");
  return r;
}
__device__ __forceinline__ void st_pairs(uint32_t* p, uint32_t a, uint32_t b, uint32_t tag) {
  asm volatile("{ .reg .b64 u, v; mov.b64 u, {%1, %3}; mov.b64 v, {%2, %3}; st.relaxed.gpu.global.v2.b64 [%0], {u, v}; }"
               ::"l"(p), "r"(a), "r"(b), "r"(tag) : "memory");
}
__device__ __forceinline__ uint4 ld_pairs(const uint32_t* p) {
  uint4 v;
  asm volatile("{ .reg .b64 u, v; ld.relaxed.gpu.global.v2.b64 {u, v}, [%4]; mov.b64 {%0, %1}, u; mov.b64 {%2, %3}, v; }"
               : "=r"(v.x), "=r"(v.y), "=r"(v.z), "=r"(v.w) : "l"(p) : "memory");
  return v;
}
__device__ __forceinline__ uint2 ld_pair(const uint32_t* p) {
  uint2 v;
  asm volatile("{ .reg .b64 u; ld.relaxed.gpu.global.b64 u, [%2]; mov.b64 {%0, %1}, u; }" : "=r"(v.x), "=r"(v.y) : "l"(p) : "memory");
  return v;
}
__device__ __forceinline__ void red_release(uint32_t* p, uint32_t v) {
  asm volatile("red.release.gpu.global.add.u32 [%0], %1;" ::"l"(p), "r"(v) : "memory");
}
__device__ __forceinline__ uint32_t ldg_nc1(const void* p) {
  uint32_t v;
  asm volatile("ld.global.nc.u32 %0, [%1];" : "=r"(v) : "l"(p));
  return v;
}
__device__ __forceinline__ uint4 ldg_nc4(const void* p) {
  uint4 v; asm volatile("ld.global.nc.L1::no_allocate.v4.u32 {%0,%1,%2,%3}, [%4];" : "=r"(v.x), "=r"(v.y), "=r"(v.z), "=r"(v.w) : "l"(p)); return v;
}
__device__ __forceinline__ uint4 ldg_stream4(const void* p) {
  uint4 v;
  asm volatile("ld.global.nc.L1::no_allocate.L2::cache_hint.v4.u32 {%0,%1,%2,%3}, [%4], %5;" : "=r"(v.x), "=r"(v.y), "=r"(v.z), "=r"(v.w) : "l"(p), "l"(l2_stream()));
  return v;
}
__device__ __forceinline__ void stg4(void* p, uint4 v) {
  asm volatile("st.global.v4.u32 [%0], {%1,%2,%3,%4};" ::"l"(p), "r"(v.x), "r"(v.y), "r"(v.z), "r"(v.w) : "memory");
}
__device__ __forceinline__ void wait_counter(const uint32_t* p, uint32_t target) {
  uint32_t n = 0;
  while ((int)(ld_acquire(p) - target) < 0) { watchdog(n); }
}
__device__ __forceinline__ uint32_t tagf(float v, uint32_t tag) { return (__float_as_uint(v) & ~3u) | tag; }
__device__ __forceinline__ bool tag_ok(uint4 v, uint32_t tag) { return (((v.x ^ tag) | (v.y ^ tag) | (v.z ^ tag) | (v.w ^ tag)) & 3u) == 0; }
__device__ __forceinline__ float untag_sum(uint32_t a, uint32_t b) { return __uint_as_float(a & ~3u) + __uint_as_float(b & ~3u); }
__device__ __forceinline__ uint4 poll4(const uint32_t* p, uint32_t tag) {
  uint4 v = ld_relaxed4(p);
  uint32_t n = 0;
  while (!tag_ok(v, tag)) { v = ld_relaxed4(p); watchdog(n); }
  return v;
}
__device__ __forceinline__ float bf_lo(uint32_t v) { return __uint_as_float(v << 16); }
__device__ __forceinline__ float bf_hi(uint32_t v) { return __uint_as_float(v & 0xffff0000u); }
__device__ __forceinline__ uint32_t pack_bf(float lo, float hi) {
  uint32_t r; asm("cvt.rn.bf16x2.f32 %0, %1, %2;" : "=r"(r) : "f"(hi), "f"(lo)); return r;
}
__device__ __forceinline__ float rbf(float v) { return __uint_as_float(pack_bf(0.f, v) & 0xffff0000u); }
__device__ __forceinline__ uint32_t hmul2(uint32_t a, uint32_t b) {
  uint32_t r; asm("mul.rn.bf16x2 %0, %1, %2;" : "=r"(r) : "r"(a), "r"(b)); return r;
}
__device__ __forceinline__ uint32_t hadd2(uint32_t a, uint32_t b) {
  uint32_t r; asm("add.rn.bf16x2 %0, %1, %2;" : "=r"(r) : "r"(a), "r"(b)); return r;
}
__device__ __forceinline__ uint32_t hsub2(uint32_t a, uint32_t b) {
  uint32_t r; asm("sub.rn.bf16x2 %0, %1, %2;" : "=r"(r) : "r"(a), "r"(b)); return r;
}
__device__ __forceinline__ uint32_t hmax2(uint32_t a, uint32_t b) {
  uint32_t r; asm("max.bf16x2 %0, %1, %2;" : "=r"(r) : "r"(a), "r"(b)); return r;
}
__device__ __forceinline__ float rcp(float x) { float r; asm("rcp.approx.ftz.f32 %0, %1;" : "=f"(r) : "f"(x)); return r; }
__device__ __forceinline__ float ex2(float x) { float r; asm("ex2.approx.ftz.f32 %0, %1;" : "=f"(r) : "f"(x)); return r; }
__device__ __forceinline__ void stmatrix4(uint32_t addr, uint32_t a, uint32_t b, uint32_t c, uint32_t d) {
  asm volatile("stmatrix.sync.aligned.m8n8.x4.shared.b16 [%0], {%1,%2,%3,%4};" ::"r"(addr), "r"(a), "r"(b), "r"(c), "r"(d) : "memory");
}
__device__ __forceinline__ void ldmatrix4(uint32_t addr, uint32_t& a, uint32_t& b, uint32_t& c, uint32_t& d) {
  asm volatile("ldmatrix.sync.aligned.m8n8.x4.shared.b16 {%0,%1,%2,%3}, [%4];" : "=r"(a), "=r"(b), "=r"(c), "=r"(d) : "r"(addr) : "memory");
}
__device__ __forceinline__ void ldmatrix4t(uint32_t addr, uint32_t& a, uint32_t& b, uint32_t& c, uint32_t& d) {
  asm volatile("ldmatrix.sync.aligned.m8n8.x4.trans.shared.b16 {%0,%1,%2,%3}, [%4];" : "=r"(a), "=r"(b), "=r"(c), "=r"(d) : "r"(addr) : "memory");
}
__device__ __forceinline__ void mma16816(float (&d)[4], uint32_t a0, uint32_t a1, uint32_t a2, uint32_t a3, uint32_t b0, uint32_t b1) {
  asm volatile("mma.sync.aligned.m16n8k16.row.col.f32.bf16.bf16.f32 {%0,%1,%2,%3}, {%4,%5,%6,%7}, {%8,%9}, {%0,%1,%2,%3};"
               : "+f"(d[0]), "+f"(d[1]), "+f"(d[2]), "+f"(d[3]) : "r"(a0), "r"(a1), "r"(a2), "r"(a3), "r"(b0), "r"(b1));
}
__device__ __forceinline__ void sts1(uint32_t a, uint32_t v) { asm volatile("st.shared.u32 [%0], %1;" ::"r"(a), "r"(v) : "memory"); }
__device__ __forceinline__ uint4 lds4(uint32_t a) {
  uint4 v; asm volatile("ld.shared.v4.u32 {%0,%1,%2,%3}, [%4];" : "=r"(v.x), "=r"(v.y), "=r"(v.z), "=r"(v.w) : "r"(a) : "memory"); return v;
}
__device__ __forceinline__ uint2 lds2(uint32_t a) {
  uint2 v; asm volatile("ld.shared.v2.u32 {%0,%1}, [%2];" : "=r"(v.x), "=r"(v.y) : "r"(a) : "memory"); return v;
}
__device__ __forceinline__ uint32_t lds1(uint32_t a) {
  uint32_t v; asm volatile("ld.shared.u32 %0, [%1];" : "=r"(v) : "r"(a) : "memory"); return v;
}
__device__ __forceinline__ void sts2(uint32_t a, uint32_t x, uint32_t y) { asm volatile("st.shared.v2.u32 [%0], {%1,%2};" ::"r"(a), "r"(x), "r"(y) : "memory"); }
__device__ __forceinline__ void sts4(uint32_t a, uint4 v) {
  asm volatile("st.shared.v4.u32 [%0], {%1,%2,%3,%4};" ::"r"(a), "r"(v.x), "r"(v.y), "r"(v.z), "r"(v.w) : "memory");
}
__device__ __forceinline__ float silu_f(float v) { return __fdividef(v, 1.f + __expf(-v)); }
__device__ __forceinline__ uint32_t hfma2(uint32_t a, uint32_t b, uint32_t c) {
  uint32_t r; asm("fma.rn.bf16x2 %0, %1, %2, %3;" : "=r"(r) : "r"(a), "r"(b), "r"(c)); return r;
}
__device__ __forceinline__ void split_inv(float sd, uint32_t& ih, uint32_t& il) {
  const float inv = rcp(sd);
  ih = pack_bf(inv, inv);
  const float lo = inv - bf_lo(ih);
  il = pack_bf(lo, lo);
}
__device__ __forceinline__ uint32_t ln_mod(uint32_t x, uint32_t mean2, uint32_t ih, uint32_t il, uint32_t c1, uint32_t sh) {
  const uint32_t d = hsub2(x, mean2);
  return hadd2(hmul2(hfma2(d, ih, hmul2(d, il)), c1), sh);
}

#define R8(a, i) "+f"(a[i]), "+f"(a[i + 1]), "+f"(a[i + 2]), "+f"(a[i + 3]), "+f"(a[i + 4]), "+f"(a[i + 5]), "+f"(a[i + 6]), "+f"(a[i + 7])
#define D64 "{%0,%1,%2,%3,%4,%5,%6,%7,%8,%9,%10,%11,%12,%13,%14,%15,%16,%17,%18,%19,%20,%21,%22,%23,%24,%25,%26,%27,%28,%29,%30,%31," \
            "%32,%33,%34,%35,%36,%37,%38,%39,%40,%41,%42,%43,%44,%45,%46,%47,%48,%49,%50,%51,%52,%53,%54,%55,%56,%57,%58,%59,%60,%61,%62,%63}"
template <int TB>
__device__ __forceinline__ void mma_ss(float (&d)[64], uint64_t da, uint64_t db, int sc) {
  asm volatile("{\n.reg .pred p;\nsetp.ne.b32 p, %66, 0;\n"
               "wgmma.mma_async.sync.aligned.m64n128k16.f32.bf16.bf16 " D64 ", %64, %65, p, 1, 1, 0, %67;\n}"
               : R8(d, 0), R8(d, 8), R8(d, 16), R8(d, 24), R8(d, 32), R8(d, 40), R8(d, 48), R8(d, 56)
               : "l"(da), "l"(db), "r"(sc), "n"(TB));
}
template <int TB>
__device__ __forceinline__ void mma_rs(float (&d)[64], uint32_t a0, uint32_t a1, uint32_t a2, uint32_t a3, uint64_t db, int sc) {
  asm volatile("{\n.reg .pred p;\nsetp.ne.b32 p, %69, 0;\n"
               "wgmma.mma_async.sync.aligned.m64n128k16.f32.bf16.bf16 " D64 ", {%64,%65,%66,%67}, %68, p, 1, 1, %70;\n}"
               : R8(d, 0), R8(d, 8), R8(d, 16), R8(d, 24), R8(d, 32), R8(d, 40), R8(d, 48), R8(d, 56)
               : "r"(a0), "r"(a1), "r"(a2), "r"(a3), "l"(db), "r"(sc), "n"(TB));
}
#define D128 "{%0,%1,%2,%3,%4,%5,%6,%7,%8,%9,%10,%11,%12,%13,%14,%15,%16,%17,%18,%19,%20,%21,%22,%23,%24,%25,%26,%27,%28,%29,%30,%31," \
             "%32,%33,%34,%35,%36,%37,%38,%39,%40,%41,%42,%43,%44,%45,%46,%47,%48,%49,%50,%51,%52,%53,%54,%55,%56,%57,%58,%59,%60,%61,%62,%63," \
             "%64,%65,%66,%67,%68,%69,%70,%71,%72,%73,%74,%75,%76,%77,%78,%79,%80,%81,%82,%83,%84,%85,%86,%87,%88,%89,%90,%91,%92,%93,%94,%95," \
             "%96,%97,%98,%99,%100,%101,%102,%103,%104,%105,%106,%107,%108,%109,%110,%111,%112,%113,%114,%115,%116,%117,%118,%119,%120,%121,%122,%123,%124,%125,%126,%127}"
#define R128(d, e) R8(d, 0), R8(d, 8), R8(d, 16), R8(d, 24), R8(d, 32), R8(d, 40), R8(d, 48), R8(d, 56), \
                   R8(e, 0), R8(e, 8), R8(e, 16), R8(e, 24), R8(e, 32), R8(e, 40), R8(e, 48), R8(e, 56)
__device__ __forceinline__ void mma256_ss(float (&d)[64], float (&e)[64], uint64_t da, uint64_t db, int sc) {
  asm volatile("{\n.reg .pred p;\nsetp.ne.b32 p, %130, 0;\n"
               "wgmma.mma_async.sync.aligned.m64n256k16.f32.bf16.bf16 " D128 ", %128, %129, p, 1, 1, 0, 1;\n}"
               : R128(d, e) : "l"(da), "l"(db), "r"(sc));
}
__device__ __forceinline__ void mma256_rs(float (&d)[64], float (&e)[64], uint32_t a0, uint32_t a1, uint32_t a2, uint32_t a3, uint64_t db) {
  asm volatile("{\n.reg .pred p;\nsetp.ne.b32 p, 1, 0;\n"
               "wgmma.mma_async.sync.aligned.m64n256k16.f32.bf16.bf16 " D128 ", {%128,%129,%130,%131}, %132, p, 1, 1, 1;\n}"
               : R128(d, e) : "r"(a0), "r"(a1), "r"(a2), "r"(a3), "l"(db));
}
template <int N> __device__ __forceinline__ void keep(float (&a)[N]) {
#pragma unroll
  for (int i = 0; i < N; i++) asm volatile("" : "+f"(a[i])::"memory");
}
template <int N> __device__ __forceinline__ void keep(uint32_t (&a)[N]) {
#pragma unroll
  for (int i = 0; i < N; i++) asm volatile("" : "+r"(a[i])::"memory");
}

#define STAMP(idx) do {} while (0)
#define PROF(grp, cond, idx) do {} while (0)

constexpr float SCL2 = 1.4426950408889634f * 0.08838834764831845f;

__device__ __forceinline__ void pack_p(const float (&s)[64], uint32_t (&p)[32]) {
#pragma unroll
  for (int i = 0; i < 32; i++) p[i] = pack_bf(s[2 * i], s[2 * i + 1]);
}

__device__ __forceinline__ void issue_qk(float (&s)[64], uint32_t q0, uint32_t q1, uint32_t kslot) {
  const uint64_t db = make_desc(kslot, 16, 1024), da0 = make_desc(q0, 16, 1024), da1 = make_desc(q1, 16, 1024);
#pragma unroll
  for (int kk = 0; kk < 8; kk++) mma_ss<0>(s, (kk < 4 ? da0 : da1) + (kk & 3) * 2, db + (kk >> 2) * 1024 + (kk & 3) * 2, kk != 0);
}
__device__ __forceinline__ void issue_pv(float (&o)[64], uint32_t (&p)[32], uint32_t vslot, int acc) {
  uint64_t db = make_desc(vslot, 16384, 1024);
#pragma unroll
  for (int kk = 0; kk < 8; kk++)
    mma_rs<1>(o, p[4 * kk], p[4 * kk + 1], p[4 * kk + 2], p[4 * kk + 3], db + kk * 128, kk == 0 ? acc : 1);
}

template <int H>
__device__ __forceinline__ void store_chunk(const float (&a)[64], uint32_t addr) {
#pragma unroll
  for (int i = 8 * H; i < 8 * H + 8; i += 2)
    stmatrix4(addr ^ ((i & 7) << 4), pack_bf(a[4 * i], a[4 * i + 1]), pack_bf(a[4 * i + 2], a[4 * i + 3]),
              pack_bf(a[4 * i + 4], a[4 * i + 5]), pack_bf(a[4 * i + 6], a[4 * i + 7]));
}
template <int H>
__device__ __forceinline__ void store_chunk(const float (&a)[64], float i0, float i1, uint32_t addr) {
#pragma unroll
  for (int i = 8 * H; i < 8 * H + 8; i += 2)
    stmatrix4(addr ^ ((i & 7) << 4), pack_bf(a[4 * i] * i0, a[4 * i + 1] * i0), pack_bf(a[4 * i + 2] * i1, a[4 * i + 3] * i1),
              pack_bf(a[4 * i + 4] * i0, a[4 * i + 5] * i0), pack_bf(a[4 * i + 6] * i1, a[4 * i + 7] * i1));
}
__device__ __forceinline__ float inv_quad_sum(float l) {
  l += __shfl_xor_sync(0xffffffffu, l, 1);
  l += __shfl_xor_sync(0xffffffffu, l, 2);
  return rcp(l);
}

__device__ __forceinline__ void ln_scalars(float mean, float var, float& mb, float& sd) {
  mb = rbf(mean);
  float r; asm("sqrt.approx.ftz.f32 %0, %1;" : "=f"(r) : "f"(rbf(rbf(var) + 1e-5f)));
  sd = rbf(r);
}

__global__ void __cluster_dims__(2, 1, 1) __launch_bounds__(384, 1) fused_kernel(const __grid_constant__ Maps maps, const Ptrs P) {
  extern __shared__ __align__(1024) uint8_t smem_raw[];
  const uint32_t base = smem_u32(smem_raw);
  const int tid = threadIdx.x, lane = tid & 31;
  const int warp = __shfl_sync(0xffffffffu, tid >> 5, 0);
  const int b = blockIdx.x;
  PROF(31, tid == 0, 0);

  if (b >= NMAIN) {
    float* sc = reinterpret_cast<float*>(smem_raw);
    float* red = sc + DM;
    for (int k = tid; k < DM; k += 384) sc[k] = rbf(silu_f(__bfloat162float(P.c[k])));
    __syncthreads();
    if (tid < 256) {
      const int col = 2048 + (b - NMAIN) * 1024 + (tid & 127) * 8, r0 = (tid >> 7) * 512;
      float acc[8];
#pragma unroll
      for (int e = 0; e < 8; e++) acc[e] = 0.f;
#pragma unroll 1
      for (int r = r0; r < r0 + 512; r += HU) {
        uint4 w[HU];
#pragma unroll
        for (int u = 0; u < HU; u++) w[u] = ldg_stream4(P.w_mod + (size_t)(r + u) * NMOD + col);
#pragma unroll
        for (int u = 0; u < HU; u++) {
          float s = sc[r + u];
          acc[0] += s * bf_lo(w[u].x); acc[1] += s * bf_hi(w[u].x); acc[2] += s * bf_lo(w[u].y); acc[3] += s * bf_hi(w[u].y);
          acc[4] += s * bf_lo(w[u].z); acc[5] += s * bf_hi(w[u].z); acc[6] += s * bf_lo(w[u].w); acc[7] += s * bf_hi(w[u].w);
        }
      }
      if (tid >= 128) {
#pragma unroll
        for (int e = 0; e < 8; e++) red[(tid & 127) * 8 + e] = acc[e];
      }
      const uint32_t tag = ld_relaxed(&g_epoch) % 3 + 1;
      bar_sync(1, 256);
      if (tid < 128) {
        uint32_t o[8];
#pragma unroll
        for (int e = 0; e < 8; e++) o[e] = __float_as_uint(rbf(acc[e] + red[tid * 8 + e])) | tag;
        st_relaxed4(g_mod + col, o[0], o[1], o[2], o[3]);
        st_relaxed4(g_mod + col + 4, o[4], o[5], o[6], o[7]);
        const uint4 wr = ldg_nc4(P.w_r + tid * 8);
        const uint32_t wv[4] = {wr.x, wr.y, wr.z, wr.w};
        float dsum = 0.f;
#pragma unroll
        for (int e = 0; e < 8; e++) {
          const float m = bf_hi(o[e]);
          dsum += (b == NMAIN + 2 ? rbf(1.f + m) : m) * ((e & 1) ? bf_hi(wv[e >> 1]) : bf_lo(wv[e >> 1]));
        }
#pragma unroll
        for (int k = 16; k > 0; k >>= 1) dsum += __shfl_xor_sync(0xffffffffu, dsum, k);
        if (lane == 0) st_relaxed(g_mod + (b - NMAIN) * 4 + warp, tagf(dsum, tag));
      }
    }
    PROF(2, tid == 0, 1);
    return;
  }

  const int rank = b & 1;
  const int rb = ((b >> 4) << 1) | rank, cj = (b >> 1) & 7;
  const uint32_t bfull = base + OFF_BAR, bempty = bfull + NSLOT * 8;
  const uint32_t gfull = bempty + NSLOT * 8, gempty = gfull + 32;
  const uint32_t bar_ofull = gempty + 32;
  const uint32_t bar_ofree = bar_ofull + 16;
  const uint32_t bar_par = bar_ofree + 32;
  const uint32_t bar_mod = bar_par + 8;
  const uint32_t bar_pread = bar_mod + 8;
  const uint32_t bar_xres = bar_pread + 8;
  const uint32_t bar_ring = bar_xres + 8;
  const uint32_t bar_box = bar_ring + 24;
  const uint32_t bar_go = bar_box + 96;
  const uint32_t bar_go2 = bar_go + 16;
  const uint32_t bar_cnt = bar_go + 24;
  const uint32_t xfull = bar_go + 32, xempty = xfull + 32;
  const uint32_t bar_hw = xempty + 32, bar_hx = bar_hw + 8;
  const uint32_t bar_hpub = bar_hx + 16;
  const uint32_t bar_win = bar_hpub + 8;
  const uint32_t bar_rx = bar_win + 8;
  const uint32_t bar_sel = bar_rx + 8;
  const uint32_t bar_gate = bar_sel + 8;
  const uint32_t bar_res = bar_go + 8;
  const uint32_t stage = base + OFF_STAGE, par = base + OFF_PAR;

  if (warp == 8 && elect_one()) {
    for (int s = 0; s < NSLOT; s++) { mbar_init(bfull + s * 8, 1); mbar_init(bempty + s * 8, 16); }
    for (int s = 0; s < 4; s++) { mbar_init(gfull + s * 8, 1); mbar_init(gempty + s * 8, 16); mbar_init(xfull + s * 8, 1); mbar_init(xempty + s * 8, 8); mbar_init(bar_ofree + s * 8, 1); }
    mbar_init(bar_ofull, 128); mbar_init(bar_ofull + 8, 128);
    mbar_init(bar_par, 64); mbar_init(bar_mod, 256); mbar_init(bar_pread, 8); mbar_init(bar_xres, 1);
    mbar_init(bar_ring, 8); mbar_init(bar_ring + 8, 8); mbar_init(bar_ring + 16, 8);
    mbar_init(bar_go, 1); mbar_init(bar_go2, 1); mbar_init(bar_cnt, 1); mbar_init(bar_hpub, 8); mbar_init(bar_res, 1); mbar_init(bar_win, 1); mbar_init(bar_rx, 1); mbar_init(bar_sel, 64); mbar_init(bar_gate, 8);
    for (int s = 0; s < 12; s++) mbar_init(bar_box + s * 8, 1);
    asm volatile("fence.mbarrier_init.release.cluster;" ::: "memory");
    prefetch_map(&maps.x); prefetch_map(&maps.wq); prefetch_map(&maps.k); prefetch_map(&maps.v);
  }
  if (warp == 9 && elect_one()) {
    mbar_init(bar_hw, 1); mbar_init(bar_hx, 1); mbar_init(bar_hx + 8, 1);
    asm volatile("fence.mbarrier_init.release.cluster;" ::: "memory");
    mbar_expect_tx(bar_hw, 32768);
    mbar_expect_tx(bar_hx, 16384);
    mbar_expect_tx(bar_hx + 8, 16384);
    const __nv_bfloat16* xs = P.x + (size_t)(rb * 128 + cj * 16) * DM;
    bulk_load(base + 2 * GST_BYTES, xs, 16384, bar_hx);
    tma2d(stage, &maps.wm, (b >> 1) * 32, rank * 512, bar_hw);
    tma2d(stage + 16384, &maps.wm, (b >> 1) * 32, rank * 512 + 256, bar_hw);
    bulk_load(base + 3 * GST_BYTES, xs + 8 * DM, 16384, bar_hx + 8);
  }
  cluster_arrive();

  if (warp >= 8) {
    asm volatile("setmaxnreg.dec.sync.aligned.u32 40;");
    if (warp < 10) bar_arrive(1, 320);
    const uint32_t epoch = ld_relaxed(&g_epoch);
    cluster_wait();
    if (warp == 8) {
      const int kvrow = (cj >> 1) * SK + (SK - WIN);
      int wch = cj * 8 + rank * 2;
#pragma unroll 1
      for (int ps = 0; ps < 3; ps++) {
        const CUtensorMap* mw = ps == 2 ? &maps.wo : &maps.wq;
        const uint32_t xt = ps == 1 ? XT1 : XT2, wt = ps == 0 ? WT0 : (ps == 1 ? WT1 : WT2);
        const int nst = ps == 2 ? 32 : 16;
        if (ps) {
          mbar_wait(bar_ofree + (ps - 1) * 16, 0);
          fence_async();
        }
#pragma unroll 1
        for (int i = 0; i < nst; i++) {
          const uint32_t bf = gfull + (i & 3) * 8;
          const int kt = ps == 2 ? (((cj & 1) * 4 + ((i >> 1) & 3)) * 4 + (i >> 3)) * 2 + (i & 1) : (i + (ps ? 0 : b & 14)) & 15;
          const uint32_t wd = base + unit_of(wt, i & 3) + rank * UNIT, xd = base + unit_of(xt, i & 3);
          const uint8_t* xs = g_act + (uint32_t)(rb * 80 + (ps - 1) * 16 + kt) * UNIT;
          if (ps == 0 && i == HD) mbar_wait(bar_mod, 0);
          if (ps && i && i < 4) mbar_wait(bempty + (i == 3 ? 3 : i - 1) * 8, 1);
          mbar_wait(gempty + (i & 3) * 8, ((i >> 2) & 1) ^ 1);
          if (elect_one()) {
            mbar_expect_tx(bf, ps ? GST_BYTES : 2 * UNIT);
            tma3d_mc<true>(wd, mw, 0, (i == 31 ? kt ^ (rank * 32) : kt) * 64, i == 31 ? cj * 2 : wch, bf);
          }
          if (ps) {
            if (i == 16) mbar_wait(bar_cnt, 0);
            if (i == 2) mbar_wait(bempty + 16, 1);
            if (elect_one()) {
              if (i == 31) bulk_load(xd, xs, UNIT, bf); else bulk_load_stream(xd, xs, UNIT, bf);
              mbar_arrive_pred(bar_go, i == GOST - 1);
              mbar_arrive_pred(bar_go2, ps * 16 + i == PG0);
              mbar_arrive_pred(bar_res, ((1u << RES0 | 1u << RES1) >> i) & 1);
              if (ps == 2 && b < NFFN && i >= PD0 && i < PD0 + 16)
                asm volatile("cp.async.bulk.prefetch.L2.global [%0], 4096;" ::"l"(P.w_down + (size_t)b * 32768 + (i - PD0) * 2048) : "memory");
            }
          }
        }
        if (ps == 2) break;
        wch = ps ? ((wch >> 3) ^ rank) * 2 : wch + 4;
#pragma unroll 1
        for (int u = 0; u < 16; u++) {
          const bool isk = (u == 0) || ((u & 1) && u < 15);
          const int blk = (isk ? (u + 1) >> 1 : (u == 15 ? 7 : (u >> 1) - 1)) & 3;
          const uint32_t sl = base + unit_of(ps ? AT1 : AT0, u & 3) + rank * UNIT, bf = bfull + (u & 3) * 8;
          if (u < 4) mbar_wait(gempty + ((u + 1) >> 1) * 8, 1);
          mbar_wait(bempty + (u & 3) * 8, ((u >> 2) & 1) ^ 1);
          if (elect_one()) {
            mbar_expect_tx(bf, SLOT_BYTES);
            tma3d_mc<false>(sl, isk ? &maps.k : &maps.v, 0, kvrow + blk * 128, rank, bf);
            if (ps && u >= PF2T && u < PF2T + 2 * PF2 && !((u - PF2T) & 1))
              tma3d_prefetch(&maps.wo, 0, ((((cj & 1) * 4 + (b >> 5)) * 4 + ((u - PF2T) >> 1)) * 2 + ((b >> 4) & 1)) * 64, (cj ^ rank) * 2);
          }
        }
      }
      mbar_wait(bar_ring, 0);
      if (elect_one()) {
        mbar_expect_tx(bar_rx, UNIT);
        bulk_load_stream(base + 8 * UNIT, g_act + (uint32_t)(rb * 80 + 16 + 63 - (cj & 1) * 32) * UNIT, UNIT, bar_rx);
      }
      if (b < NFFN) {
#pragma unroll 1
        for (int u = 0; u < 12; u++) {
          if (u == 2 || u == 8) mbar_wait(bar_ring + 8 + (u & 8), 0);
          if (u >= FPACE) mbar_wait(bar_box + (u - FPACE) * 8, 0);
          const uint32_t dst = base + unit_of(u < 4 ? FT_G : (u < 8 ? FT_U : FT_D), u & 3);
          if (elect_one()) {
            mbar_expect_tx(bar_box + u * 8, UNIT);
            if (u < 8) tma2d(dst, u < 4 ? &maps.wg : &maps.wu, b * 32, (u & 3) * 256, bar_box + u * 8);
            else tma3d(dst, &maps.wd, 0, b * 32, (u - 8) * 4, bar_box + u * 8);
          }
        }
      }
    } else if (warp == 9) {
      const uint32_t target = 8 * (epoch + 1);
#pragma unroll 1
      for (int i = 0; i < 16; i++) {
        if (i == HDX) mbar_wait(bar_mod, 0);
        if (i == NRS) {
          wait_counter(&g_cnt_h[rb * 32], target);
          PROF(1, lane == 0, 26);
          fence_async();
        }
        mbar_wait(xempty + (i & 3) * 8, ((i >> 2) & 1) ^ 1);
        if (elect_one()) {
          mbar_expect_tx(xfull + (i & 3) * 8, UNIT);
          if (i < NRS) tma2d(base + (i & 3) * GST_BYTES, &maps.x, ((2 * cj + i) & 15) * 64, rb * 128, xfull + (i & 3) * 8);
          else bulk_load_stream(base + (i & 3) * GST_BYTES, g_act + (uint32_t)(rb * 80 + ((2 * cj + i) & 15)) * UNIT, UNIT, xfull + (i & 3) * 8);
        }
      }
      prefetch_map(&maps.wo);
#pragma unroll 1
      for (int t = 0; t < 4; t++) {
#pragma unroll 1
        for (int w = 0; w < 2; w++) {
          mbar_wait(bar_ofull + w * 8, t & 1);
          uint8_t* dst = g_act + (uint32_t)(rb * 80 + 16 + (cj * 4 + t) * 2) * UNIT + w * 8192;
          if (elect_one()) {
            bulk_store(dst, base + unit_of(QT, 2 * t) + w * 8192, 8192);
            bulk_store(dst + UNIT, base + unit_of(QT, 2 * t + 1) + w * 8192, 8192);
            asm volatile("cp.async.bulk.commit_group;" ::: "memory");
          }
        }
        if (elect_one()) {
          asm volatile("cp.async.bulk.wait_group.read 0;" ::: "memory");
          mbar_arrive(bar_ofree + t * 8);
          asm volatile("cp.async.bulk.wait_group 0;" ::: "memory");
          fence_async();
          red_release(&g_cnt_o[((rb * 4 + t) * 2 + (cj >> 2)) * 32], 2);
        }
        if (t & 1) {
          wait_counter(&g_cnt_o[(rb * 8 + 2 * t - 2 + (cj & 1)) * 32], target);
          wait_counter(&g_cnt_o[(rb * 8 + 2 * t + (cj & 1)) * 32], target);
        }
      }
      wait_counter(&g_cnt_o[(rb * 8 + 7 - (cj & 1)) * 32], target);
      fence_async();
      if (elect_one()) {
        mbar_arrive(bar_cnt);
        PROF(2, true, 27);
        mbar_expect_tx(bar_xres, 32768);
      }
#pragma unroll 1
      for (int u = 0; u < 2; u++) {
        mbar_wait(bar_res, u);
        if (elect_one()) tma2d(base + OFF_RES + u * UNIT, &maps.x, cj * 128 + u * 64, rb * 128, bar_xres);
      }
      const uint32_t tag = epoch % 3 + 1;
      const uint32_t* inbox = g_cand + b * 32 + (lane & 15);
      mbar_wait(bar_ring + 16, 0);
      uint32_t c0 = ld_relaxed(inbox);
      __nanosleep(PSL);
      uint32_t c1 = ld_relaxed(inbox);
      __nanosleep(PSL);
      uint32_t c2 = ld_relaxed(inbox), n = 0;
#define CAND_STEP(cv)                                                                                        \
      {                                                                                                      \
        const bool valid = (cv & 3u) == tag, all = __all_sync(0xffffffffu, valid);                           \
        const uint32_t best = __reduce_max_sync(0xffffffffu, valid ? cv : 0u);                               \
        const uint32_t blk = __ffs(__ballot_sync(0xffffffffu, cv == best)) - 1;                              \
        if (best) sts2(par + PAR_CONST + 56, best, (blk << 7 | (~best >> 2 & 127)) | (all ? 0x1800 : 0x800)); \
        if (all) break;                                                                                      \
        cv = ld_relaxed(inbox);                                                                              \
      }
      while (true) { CAND_STEP(c0) CAND_STEP(c1) CAND_STEP(c2) watchdog(n); }
    } else {
      const int t2 = tid - 320;
      if (t2 == 0) {
        mbar_wait(bar_hpub, 0);
        PROF(1, true, 24);
        red_release(&g_cnt_h[rb * 32], 1);
        PROF(1, true, 25);
        prefetch_map(&maps.wg); prefetch_map(&maps.wu); prefetch_map(&maps.wd); prefetch_map(&maps.out);
      }
      __syncwarp();
      if (b < NFFN) {
        mbar_wait(bar_go2, 0);
        const __nv_bfloat16* pg = ((b & 1) ? P.w_up : P.w_gate) + (b >> 1) * 64 + (size_t)t2 * FF;
        const __nv_bfloat16* pd = P.w_down + (size_t)b * 32768 + t2 * 64;
        PROF(2, t2 == 0, 13);
#pragma unroll 1
        for (int i = 0; i < WN; i += WB) {
          uint32_t v[WB];
#pragma unroll
          for (int u = 0; u < WB; u++)
            asm volatile("ld.global.cg.L2::128B.u32 %0, [%1];" : "=r"(v[u]) : "l"(i < 16 ? pg + (size_t)(i + u) * 64 * FF : pd + (i + u - 16) * 4096));
#pragma unroll
          for (int u = 1; u < WB; u++) v[0] ^= v[u];
          sts1(par + PAR_SINK + t2 * 4, v[0]);
        }
        PROF(2, t2 == 0, 14);
      }
      const uint32_t tag = epoch % 3 + 1;
      mbar_wait(bar_go, 0);
      if (warp == 10) {
        const uint32_t* src = g_mod + 2 * DM + cj * 128 + lane * 4;
        const uint2 wr = *reinterpret_cast<const uint2*>(P.w_r + cj * 128 + lane * 4);
        uint4 vga, vsb, vcb, vgb;
        uint32_t n = 0;
        do {
          vga = ld_relaxed4(src); vsb = ld_relaxed4(src + DM); vcb = ld_relaxed4(src + 2 * DM); vgb = ld_relaxed4(src + 3 * DM);
          watchdog(n);
        } while (!(tag_ok(vga, tag) && tag_ok(vsb, tag) && tag_ok(vcb, tag) && tag_ok(vgb, tag)));
        const float c0 = rbf(1.f + bf_hi(vcb.x)), c1 = rbf(1.f + bf_hi(vcb.y)), c2 = rbf(1.f + bf_hi(vcb.z)), c3 = rbf(1.f + bf_hi(vcb.w));
        const float a0 = c0 * bf_lo(wr.x), a1 = c1 * bf_hi(wr.x), a2 = c2 * bf_lo(wr.y), a3 = c3 * bf_hi(wr.y);
        const uint32_t h0 = pack_bf(a0, a1), h1 = pack_bf(a2, a3);
        const uint32_t t1 = par + PAR_T1 + (lane >> 2) * 64 + (lane & 1) * 32 + (lane & 2) * 2;
        sts1(t1, h0); sts1(t1 + 8, pack_bf(a0 - bf_lo(h0), a1 - bf_hi(h0)));
        sts1(t1 + 16, h1); sts1(t1 + 24, pack_bf(a2 - bf_lo(h1), a3 - bf_hi(h1)));
        sts4(par + PAR_T2 + lane * 32, make_uint4(pack_bf(c0, c1), __byte_perm(vsb.x, vsb.y, 0x7632), __byte_perm(vgb.x, vgb.y, 0x7632), __byte_perm(vga.x, vga.y, 0x7632)));
        sts4(par + PAR_T2 + lane * 32 + 16, make_uint4(pack_bf(c2, c3), __byte_perm(vsb.z, vsb.w, 0x7632), __byte_perm(vgb.z, vgb.w, 0x7632), __byte_perm(vga.z, vga.w, 0x7632)));
      } else if (lane < 4) {
        const uint4 g = poll4(lane < 2 ? g_mod + 5 * DM + b * 8 + lane * 4 : g_mod + 16 - lane * 4, tag);
        sts1(par + PAR_CONST + 60, 0);
        if (lane < 2) sts4(par + PAR_CONST + 16 + lane * 16, g);
        else sts2(par + PAR_CONST + (lane - 2) * 8, __float_as_uint(untag_sum(g.x, g.y) + untag_sum(g.z, g.w)), epoch);
      }
      __syncwarp();
#pragma unroll 4
      for (int q = XR; q < XE; q++) st_b128(g_xch + ((size_t)b * 8 * 256 + q * 64 + t2) * 4, (epoch & 1) << 16, 0, 0, 0);
      for (int q = 0; q < 2; q++) st_relaxed4(g_stats + ((size_t)cj * SEQ + rb * 128 + q * 64 + t2) * 4, 0, 0, 0, 0);
      if (b < NFFN)
        for (int q = 0; q < 4; q++) st_relaxed4(g_ypart + ((size_t)(q * 32 + (t2 >> 1)) * NFFN + b) * 8 + (t2 & 1) * 4, 0, 0, 0, 0);
      st_relaxed4(g_row + rb * 2 * DM + (t2 >> 5) * DM + cj * 128 + (t2 & 31) * 4, 0, 0, 0, 0);
      if (t2 < 16) st_relaxed(g_cand + (cj * 16 + t2) * 32 + rb, 0);
      __threadfence();
      mbar_arrive(bar_par);
      mbar_wait(bar_gate, 0);
      uint32_t have = 0, n = 0;
      while (true) {
        const uint32_t st = lds1(par + PAR_CONST + 60) >> 7;
        if ((st & 31) != have) {
          const uint32_t* hsrc = g_row + (st & 15) * 2 * DM + t2 * 4;
          uint4 hv[4];
          bool ok = true;
#pragma unroll
          for (int i = 0; i < 4; i++) hv[i] = ld_pairs(hsrc + i * 256);
#pragma unroll
          for (int i = 0; i < 4; i++) {
            sts2(base + ((FT_G >> i * 4) & 15) * UNIT + (warp & 1) * 8192 + 256 + lane * 8, hv[i].x, hv[i].z);
            ok = ok && hv[i].y == tag && hv[i].w == tag;
          }
          have = __all_sync(0xffffffffu, ok) ? st & 31 : 0;
        }
        if ((st ^ have) == 32) break;
        watchdog(n);
      }
      mbar_arrive(bar_sel);
    }
    __syncwarp();
    cluster_arrive();
    {
      const uint32_t tag = epoch % 3 + 1, t3 = tid - 256;
      mbar_wait(bar_win, 0);
      uint2 win = lds2(par + PAR_CONST + 56);
      win.y &= 0x7ff;
      const uint32_t* fsrc = g_row + (win.y >> 7) * 2 * DM + (b >> 1) * 16 + (t3 & 3) * 4 + (b & 1) * 2;
      const uint32_t* ysrc = g_ypart + ((size_t)b * NFFN + min(t3, NFFN - 1)) * 8;
      uint2 fh = ld_pair(fsrc), fx = ld_pair(fsrc + DM);
      uint4 ya = ld_relaxed4(ysrc), yb = ld_relaxed4(ysrc + 4);
      const float rwin = __uint_as_float(((int)win.x < 0 ? win.x & 0x7fffffffu : ~win.x) & ~0x1ffu);
      const float rs = rbf(rcp(1.f + __expf(-rbf(rwin))));
      uint32_t n = 0;
      while (fh.y != tag || fx.y != tag) { fh = ld_pair(fsrc); fx = ld_pair(fsrc + DM); watchdog(n); }
      while (!(tag_ok(ya, tag) && tag_ok(yb, tag))) { ya = ld_relaxed4(ysrc); yb = ld_relaxed4(ysrc + 4); watchdog(n); }
      __syncwarp();
      PROF(8, t3 == 0, 5);
      const uint32_t msk = t3 < NFFN ? ~3u : 0u;
      float y[8] = {__uint_as_float(ya.x & msk), __uint_as_float(ya.y & msk), __uint_as_float(ya.z & msk), __uint_as_float(ya.w & msk),
                    __uint_as_float(yb.x & msk), __uint_as_float(yb.y & msk), __uint_as_float(yb.z & msk), __uint_as_float(yb.w & msk)};
#pragma unroll
      for (int h = 4; h > 0; h >>= 1) {
        const bool up = lane & (h * 4);
#pragma unroll
        for (int e = 0; e < h; e++) y[e] = (up ? y[e + h] : y[e]) + __shfl_xor_sync(0xffffffffu, up ? y[e] : y[e + h], h * 4);
      }
      y[0] += __shfl_xor_sync(0xffffffffu, y[0], 1);
      y[0] += __shfl_xor_sync(0xffffffffu, y[0], 2);
      if ((lane & 3) == 0) sts1(par + PAR_RED + 64 + t3, __float_as_uint(y[0]));
      bar_sync(4, 128);
      if (t3 < 4) {
        float y0 = 0.f, y1 = 0.f;
#pragma unroll
        for (int w4 = 0; w4 < 4; w4++) {
          const uint2 v = lds2(par + PAR_RED + 64 + w4 * 32 + t3 * 8);
          y0 += __uint_as_float(v.x); y1 += __uint_as_float(v.y);
        }
        const uint2 gv = lds2(par + PAR_CONST + 16 + t3 * 8);
        const uint32_t upd = hmul2(pack_bf(y0, y1), pack_bf(rs, rs));
        *reinterpret_cast<uint32_t*>(P.out + (size_t)win.y * DM + b * 8 + t3 * 2) =
            hadd2(fx.x, hmul2(__byte_perm(gv.x, gv.y, 0x7632), hadd2(fh.x, upd)));
        if (b == 0 && t3 == 0) st_relaxed(&g_epoch, epoch + 1);
      }
      PROF(31, t3 == 0, 36);
    }
    cluster_wait();
  } else {
    const int wg = warp >> 2;

    uint32_t tag;
    {
      uint32_t* const pmod = g_modp + rank * 2 * DM + (b >> 1) * 32 + lane;
      uint32_t* const pln = g_ln1 + (rb * 128 + cj * 16 + warp) * 4;
      const uint32_t cv = ldg_nc1(P.c + rank * 512 + tid * 2);
      const uint32_t epoch = ld_relaxed(&g_epoch);
      if (warp == 0) st_relaxed(pmod, 0);
      if (lane == 0) { st_relaxed2(pln, 0, 0); st_relaxed2(pln + 32, 0, 0); }
      asm volatile("setmaxnreg.inc.sync.aligned.u32 232;");
      sts1(par + tid * 4, pack_bf(silu_f(bf_lo(cv)), silu_f(bf_hi(cv))));
      bar_sync(1, 320);
      tag = epoch % 3 + 1;
#pragma unroll
      for (int part = 0; part < 3; part++) {
        if (part != 1) {
          const uint32_t xa = base + (2 + part / 2) * GST_BYTES + warp * 2048 + lane * 16;
          mbar_wait(bar_hx + part * 4, 0);
          float s0 = 0.f, s1 = 0.f, q0 = 0.f, q1 = 0.f;
#pragma unroll
          for (int q = 0; q < 4; q++) {
            const uint4 xv = lds4(xa + q * 512);
            const uint32_t u[4] = {xv.x, xv.y, xv.z, xv.w};
#pragma unroll
            for (int e = 0; e < 4; e++) { const float lo = bf_lo(u[e]), hi = bf_hi(u[e]); s0 += lo; s1 += hi; q0 += lo * lo; q1 += hi * hi; }
          }
          s0 += s1; q0 += q1;
#pragma unroll
          for (int o = 16; o > 0; o >>= 1) { s0 += __shfl_xor_sync(0xffffffffu, s0, o); q0 += __shfl_xor_sync(0xffffffffu, q0, o); }
          const float mean = s0 * (1.f / DM);
          float mb, sd;
          ln_scalars(mean, fmaxf(q0 * (1.f / DM) - mean * mean, 0.f), mb, sd);
          if (lane == 0) st_relaxed2(pln + part * 16, __float_as_uint(mb) | tag, __float_as_uint(sd) | tag);
          PROF(1, tid == 0 && part == 2, 4);
        } else {
          float acc[8];
#pragma unroll
          for (int e = 0; e < 8; e++) acc[e] = 0.f;
          const uint32_t wa = stage + (tid >> 2) * 64 + (((tid ^ (tid >> 3)) & 3) << 4), sa = par + (tid >> 3) * 4, sh = (tid & 4) ? 0x3244 : 0x1044;
          mbar_wait(bar_hw, 0);
#pragma unroll
          for (int p = 0; p < 8; p++) {
            const uint4 w = lds4(wa + p * 4096);
            const float s = __uint_as_float(__byte_perm(lds1(sa + p * 128), 0, sh));
            acc[0] += s * bf_lo(w.x); acc[1] += s * bf_hi(w.x); acc[2] += s * bf_lo(w.y); acc[3] += s * bf_hi(w.y);
            acc[4] += s * bf_lo(w.z); acc[5] += s * bf_hi(w.z); acc[6] += s * bf_lo(w.w); acc[7] += s * bf_hi(w.w);
          }
#pragma unroll
          for (int e = 0; e < 4; e++) {
            const bool up = lane & 16;
            acc[e] = (up ? acc[e + 4] : acc[e]) + __shfl_xor_sync(0xffffffffu, up ? acc[e] : acc[e + 4], 16);
          }
#pragma unroll
          for (int e = 0; e < 2; e++) {
            const bool up = lane & 8;
            acc[e] = (up ? acc[e + 2] : acc[e]) + __shfl_xor_sync(0xffffffffu, up ? acc[e] : acc[e + 2], 8);
          }
          {
            const bool up = lane & 4;
            acc[0] = (up ? acc[1] : acc[0]) + __shfl_xor_sync(0xffffffffu, up ? acc[0] : acc[1], 4);
          }
          sts1(par + 1024 + warp * 128 + ((lane & 3) * 8 + (lane >> 2)) * 4, __float_as_uint(acc[0]));
          bar_sync(1, 256);
          if (warp == 0) {
            float s = 0.f;
#pragma unroll
            for (int w8 = 0; w8 < 8; w8++) s += __uint_as_float(lds1(par + 1024 + w8 * 128 + lane * 4));
            st_relaxed(pmod, (__float_as_uint(s) & ~3u) | tag);
          }
          PROF(1, tid == 0, 3);
        }
      }
      {
        uint2 s0 = ld_relaxed2(g_ln1 + (rb * 128 + (tid & 127)) * 4);
        uint4 v[4];
#pragma unroll
        for (int q = 0; q < 4; q++) v[q] = ld_relaxed4(g_modp + q * DM + tid * 4);
        {
          uint32_t n = 0;
          while (!(tag_ok(v[0], tag) && tag_ok(v[1], tag) && tag_ok(v[2], tag) && tag_ok(v[3], tag))) {
#pragma unroll
            for (int q = 0; q < 4; q++)
              if (!tag_ok(v[q], tag)) v[q] = ld_relaxed4(g_modp + q * DM + tid * 4);
            if (((s0.x ^ tag) | (s0.y ^ tag)) & 3u) s0 = ld_relaxed2(g_ln1 + (rb * 128 + (tid & 127)) * 4);
            watchdog(n);
          }
        }
        const uint32_t d = stage + (tid >> 2) * 64 + (tid & 1) * 32 + (tid & 2) * 2;
        sts1(d, pack_bf(1.f + rbf(untag_sum(v[1].x, v[3].x)), 1.f + rbf(untag_sum(v[1].y, v[3].y))));
        sts1(d + 16, pack_bf(1.f + rbf(untag_sum(v[1].z, v[3].z)), 1.f + rbf(untag_sum(v[1].w, v[3].w))));
        sts1(d + 8, pack_bf(untag_sum(v[0].x, v[2].x), untag_sum(v[0].y, v[2].y)));
        sts1(d + 24, pack_bf(untag_sum(v[0].z, v[2].z), untag_sum(v[0].w, v[2].w)));
        if (wg == 0) {
          uint32_t n = 0;
          while (((s0.x ^ tag) | (s0.y ^ tag)) & 3u) { s0 = ld_relaxed2(g_ln1 + (rb * 128 + tid) * 4); watchdog(n); }
          uint32_t ih, il;
          split_inv(bf_hi(s0.y), ih, il);
          sts4(stage + 4096 + tid * 16, make_uint4(__byte_perm(s0.x, 0, 0x3232), ih, il, 0));
        }
        mbar_arrive(bar_mod);
      }
      cluster_wait();
      if (wg == 1) bar_arrive(2, 256);
      mbar_wait(bar_mod, 0);
      PROF(1, tid == 0, 2);
    }

    float f0 = 0.f, f1 = 0.f;
    const uint32_t rempty = lane < 2 ? mapa(bempty, lane & 1) : 0;
    constexpr uint32_t GE = NSLOT * 8 + 32;
    float o[64], s[64];
#pragma unroll 1
    for (int ps = 0; ps < 3; ps++) {
      {
        const uint32_t xt = ps == 1 ? XT1 : XT2, wt = ps == 1 ? WT1 : WT2;
        const int nst = ps == 2 ? 28 : 14;
        if (ps == 0) {
          float ga[64], gb[64];
#pragma unroll
          for (int i = 0; i < 64; i++) { ga[i] = 0.f; gb[i] = 0.f; }
          uint32_t a[2][16];
          const uint32_t l = fresh_lane();
          const uint4 r0 = lds4(stage + 4096 + (warp * 16 + (l >> 2)) * 16), r1 = lds4(stage + 4096 + 128 + (warp * 16 + (l >> 2)) * 16);
          auto transform = [&](int i, uint32_t (&f)[16], uint32_t z) {
            const uint32_t ad = base + (i & 3) * GST_BYTES + wg * 8192 + frag_offset(warp) + z;
            mbar_wait(xfull + (i & 3) * 8, i >> 2);
#pragma unroll
            for (int kk = 0; kk < 4; kk++) ldmatrix4(ad ^ (kk * 32), f[4 * kk], f[4 * kk + 1], f[4 * kk + 2], f[4 * kk + 3]);
#pragma unroll
            for (int kk = 0; kk < 4; kk++) {
              const uint4 m = lds4(stage + (l & 3) * 16 + ((2 * cj + i) & 15) * 256 + kk * 64);
              f[4 * kk] = ln_mod(f[4 * kk], r0.x, r0.y, r0.z, m.x, m.z);
              f[4 * kk + 1] = ln_mod(f[4 * kk + 1], r1.x, r1.y, r1.z, m.x, m.z);
              f[4 * kk + 2] = ln_mod(f[4 * kk + 2], r0.x, r0.y, r0.z, m.y, m.w);
              f[4 * kk + 3] = ln_mod(f[4 * kk + 3], r1.x, r1.y, r1.z, m.y, m.w);
            }
            keep(f);
            mbar_arrive_pred(xempty + (i & 3) * 8, l == 0);
          };
          auto publish = [&](int u, uint32_t (&f)[16]) {
            const uint32_t sc = stage + 8192 + wg * 8192;
#pragma unroll
            for (int kk = 0; kk < 4; kk++) stmatrix4((sc + frag_offset(warp)) ^ (kk * 32), f[4 * kk], f[4 * kk + 1], f[4 * kk + 2], f[4 * kk + 3]);
            __syncwarp();
            const uint32_t src = sc + (warp & 3) * 2048 + l * 16;
            uint8_t* dst = g_act + (uint32_t)(rb * 80 + cj * 2 + u) * UNIT + warp * 2048 + l * 16;
#pragma unroll
            for (int p4 = 0; p4 < 4; p4++) stg4(dst + p4 * 512, lds4(src + p4 * 512));
            __syncwarp();
            if (u == 1) mbar_arrive_pred(bar_hpub, l == 0);
          };
          auto multiply = [&](int i, uint32_t (&f)[16]) {
            mbar_wait(gfull + (i & 3) * 8, i >> 2);
            const uint64_t db = make_desc(base + (i & 3) * GST_BYTES + UNIT, 8192, 1024);
            wg_fence();
#pragma unroll
            for (int kk = 0; kk < 4; kk++) mma256_rs(ga, gb, f[4 * kk], f[4 * kk + 1], f[4 * kk + 2], f[4 * kk + 3], db + kk * 128);
            wg_commit();
          };
          transform(0, a[0], 0); publish(0, a[0]); transform(1, a[1], 0); multiply(0, a[0]); publish(1, a[1]);
#pragma unroll
          for (int i = 1; i < NRS; i++) {
            if (i >= 2) {
              uint32_t z = r0.w;
#pragma unroll
              for (int k = 0; k < 16; k += 2) asm volatile("lop3.b32 %0, %1, %2, %0, 0xA8;" : "+r"(z) : "r"(a[i & 1][k]), "r"(a[i & 1][k + 1]));
              transform(i, a[i & 1], z);
            }
            multiply(i, a[i & 1]);
            wg_wait<1>();
            mbar_arrive_cl(rempty, GE + ((i + 3) & 3) * 8);
          }
          mbar_arrive_pred(bar_pread, l == 0);
#pragma unroll 1
          for (int i = NRS; i < 14; i++) {
            mbar_wait(xfull + (i & 3) * 8, (i >> 2) & 1);
            mbar_wait(gfull + (i & 3) * 8, (i >> 2) & 1);
            const uint32_t xa = base + (i & 3) * GST_BYTES;
            const uint64_t da = make_desc(xa + wg * 8192, 16, 1024), db = make_desc(xa + UNIT, 8192, 1024);
            if (i == 13) bar_sync(2 + wg, 256);
            wg_fence();
#pragma unroll
            for (int kk = 0; kk < 4; kk++) mma256_ss(ga, gb, da + kk * 2, db + kk * 128, 1);
            wg_commit();
            if (i == 13) bar_arrive(3 - wg, 256);
            wg_wait<1>();
            uint32_t z = r0.w;
#pragma unroll
            for (int k = 0; k < 16; k += 2) asm volatile("lop3.b32 %0, %1, %2, %0, 0xA8;" : "+r"(z) : "r"(a[1][k]), "r"(a[1][k + 1]));
            mbar_arrive_cl(rempty, GE + ((i + 3) & 3) * 8 + z);
            mbar_arrive_pred(xempty + ((i + 3) & 3) * 8, l == 0 && i != NRS);
          }
          mbar_wait(xfull + 16, 1);
          mbar_wait(xfull + 24, 1);
          wg_wait<0>();
          keep(ga); keep(gb);
#pragma unroll
          for (int i = 0; i < 64; i++) {
            asm volatile("mov.b32 %0, %1;" : "=f"(s[i]) : "f"(ga[i]));
            asm volatile("mov.b32 %0, %1;" : "=f"(o[i]) : "f"(gb[i]));
          }
        } else {
          float ga[64], gb[64];
#pragma unroll
          for (int i = 0; i < 64; i++) {
            asm volatile("mov.b32 %0, %1;" : "=f"(ga[i]) : "f"(s[i]));
            asm volatile("mov.b32 %0, %1;" : "=f"(gb[i]) : "f"(o[i]));
          }
#pragma unroll 1
          for (int i = 0; i < nst; i++) {
            mbar_wait(gfull + (i & 3) * 8, (i >> 2) & 1);
            const uint64_t da = make_desc(base + unit_of(xt, i & 3) + wg * 8192, 16, 1024), db = make_desc(base + unit_of(wt, i & 3), 8192, 1024);
            if (i == nst - 1) bar_sync(2 + wg, 256);
            wg_fence();
#pragma unroll
            for (int kk = 0; kk < 4; kk++) mma256_ss(ga, gb, da + kk * 2, db + kk * 128, kk ? 1 : i);
            wg_commit();
            if (i == nst - 1) bar_arrive(3 - wg, 256);
            wg_wait<1>();
            mbar_arrive_cl(rempty, GE + ((i + 3) & 3) * 8, i != 0);
            PROF(4, tid == 0 && (i & 3) == 0, 40 + (ps - 1) * 4 + i / 4);
          }
          wg_wait<0>();
          keep(ga); keep(gb);
#pragma unroll
          for (int i = 0; i < 64; i++) {
            asm volatile("mov.b32 %0, %1;" : "=f"(s[i]) : "f"(ga[i]));
            asm volatile("mov.b32 %0, %1;" : "=f"(o[i]) : "f"(gb[i]));
          }
        }
        mbar_arrive_cl(rempty, GE + (ps == 2 ? 24 : 8));
        if (ps == 2) break;
      }
      const uint32_t qw = base + wg * 8192, qt = QT >> (16 * ps), at = ps ? AT1 : AT0;
      {
        const uint32_t wt = ps ? WT1 : WT0;
        const uint64_t da0 = make_desc(qw + unit_of(qt, 2), 16, 1024), da1 = make_desc(qw + unit_of(qt, 3), 16, 1024);
        const uint64_t db0 = make_desc(base + unit_of(wt, 2), 8192, 1024), db1 = make_desc(base + unit_of(wt, 3), 8192, 1024);
        mbar_wait(gfull + 16, 1);
        mbar_wait(gfull + 24, 1);
        bar_sync(2 + wg, 256);
        wg_fence();
#pragma unroll
        for (int kk = 0; kk < 8; kk++) mma_ss<1>(s, (kk < 4 ? da0 : da1) + (kk & 3) * 2, (kk < 4 ? db0 : db1) + (kk & 3) * 128, 1);
        wg_commit();
        bar_arrive(3 - wg, 256);
        mbar_wait(ps == 0 ? bar_pread : bar_ofree + 8, 0);
        mbar_wait(bfull, 0);
        wg_wait<0>();
        keep(s);
        PROF(2, tid == 0, 8 + ps * 8);
        store_chunk<0>(s, qw + unit_of(qt, 0) + frag_offset(warp));
        store_chunk<1>(s, qw + unit_of(qt, 1) + frag_offset(warp));
        fence_async_smem();
        bar_sync(2 + wg, 256);
        wg_fence();
        issue_qk(s, qw + unit_of(qt, 0), qw + unit_of(qt, 1), base + unit_of(at, 0));
        wg_commit();
#pragma unroll
        for (int kk = 0; kk < 8; kk++) mma_ss<1>(o, (kk < 4 ? da0 : da1) + (kk & 3) * 2, (kk < 4 ? db0 : db1) + UNIT / 16 + (kk & 3) * 128, 1);
        wg_commit();
        bar_arrive(3 - wg, 256);
        wg_wait<1>();
        keep(s);
        mbar_arrive_cl(rempty, 0);
      }
      PROF(4, tid == 0 && ps == 1, 61);
      float l0 = 0.25f, l1 = 0.25f;
      auto step = [&](auto odd_c, const int j, uint32_t (&pw)[32], uint32_t (&pr)[32]) {
        constexpr bool ODD = decltype(odd_c)::value;
        const bool first = !ODD && (j & 2) == 0, last = ODD && j == 7;
        const uint32_t ph = (j >> 1) & 1;
        float i0, i1, a0, a1;
        if (first) { i0 = inv_quad_sum(l0); i1 = inv_quad_sum(l1); l0 = 0.f; l1 = 0.f; }
        bool redo = !ODD && (j | ps) == 0, again = false;
        while (true) {
          if (redo) {
            float m0 = fmaxf(s[0], s[1]), m1 = fmaxf(s[2], s[3]);
#pragma unroll
            for (int i = 1; i < 16; i++) { m0 = fmaxf(m0, fmaxf(s[4 * i], s[4 * i + 1])); m1 = fmaxf(m1, fmaxf(s[4 * i + 2], s[4 * i + 3])); }
            m0 = fmaxf(m0, __shfl_xor_sync(0xffffffffu, m0, 1)); m1 = fmaxf(m1, __shfl_xor_sync(0xffffffffu, m1, 1));
            m0 = fmaxf(m0, __shfl_xor_sync(0xffffffffu, m0, 2)); m1 = fmaxf(m1, __shfl_xor_sync(0xffffffffu, m1, 2));
            m0 *= SCL2; m1 *= SCL2;
            if (!first) {
              m0 = fmaxf(m0, f0); m1 = fmaxf(m1, f1);
              const float c0 = ex2(f0 - m0), c1 = ex2(f1 - m1);
              l0 *= c0; l1 *= c1;
              wg_wait<0>();
              keep(o);
#pragma unroll
              for (int i = 0; i < 16; i++) { o[4 * i] *= c0; o[4 * i + 1] *= c0; o[4 * i + 2] *= c1; o[4 * i + 3] *= c1; }
            }
            f0 = m0; f1 = m1;
          }
          float b0 = 0.f, b1 = 0.f;
          a0 = 0.f; a1 = 0.f;
#pragma unroll
          for (int i = 0; i < 16; i++) {
            const float e0 = ex2(fmaf(s[4 * i], SCL2, -f0)), e1 = ex2(fmaf(s[4 * i + 1], SCL2, -f0));
            const float e2 = ex2(fmaf(s[4 * i + 2], SCL2, -f1)), e3 = ex2(fmaf(s[4 * i + 3], SCL2, -f1));
            a0 += e0; b0 += e1; a1 += e2; b1 += e3;
            pw[2 * i] = pack_bf(e0, e1); pw[2 * i + 1] = pack_bf(e2, e3);
            if (i == VREL) {
#pragma unroll
              for (int k = 0; k < 2 * VREL + 2; k++) asm volatile("" : "+r"(pw[k])::"memory");
              mbar_wait(bfull + (ODD ? 24 : 8), ph);
              wg_wait<0>();
              mbar_arrive_cl(rempty, ODD ? 16 : (j ? 0 : GE + 16), !again);
              if (!ODD) mbar_arrive_cl(rempty, GE + 24, !again && j == 0);
#pragma unroll
              for (int k = 4 * VREL + 4; k < 64; k++) asm volatile("" : "+f"(s[k])::"memory");
            }
          }
          a0 += b0; a1 += b1;
          if (redo) break;
          redo = __any_sync(0xffffffffu, !(a0 + a1 < 0x1p70f));
          if (first) {
            uint32_t m0 = __ballot_sync(0xffffffffu, a0 > 0x1p-50f), m1 = __ballot_sync(0xffffffffu, a1 > 0x1p-50f);
            m0 |= m0 >> 1; m1 |= m1 >> 1; m0 |= m0 >> 2; m1 |= m1 >> 2;
            redo = redo || (m0 & m1 & 0x11111111u) != 0x11111111u;
          }
          if (!redo) break;
          again = true;
        }
        l0 += a0; l1 += a1;
        keep(pw);
        keep(o);
        const uint32_t qo = qt >> (j ? 0 : 8);
        if (first) store_chunk<0>(o, i0, i1, qw + unit_of(qo, 0) + frag_offset(warp));
        keep(o);
        bar_sync(2 + wg, 256);
        if (!last) {
          const uint32_t qn = qt >> (j >= 3 ? 8 : 0);
          wg_fence();
          issue_qk(s, qw + unit_of(qn, 0), qw + unit_of(qn, 1), base + unit_of(at, ODD ? 3 : 1));
          wg_commit();
          mbar_wait(bfull + (ODD ? 0 : 16), ODD ? ph ^ 1 : ph);
        }
        if (first) { store_chunk<1>(o, i0, i1, qw + unit_of(qo, 1) + frag_offset(warp)); keep(o); }
        wg_fence();
        issue_pv(o, pw, base + unit_of(at, ODD ? (last ? 3 : 0) : 2), !first);
        wg_commit();
        bar_arrive(3 - wg, 256);
        if (first) { fence_async_smem(); mbar_arrive_pred(bar_ofull + wg * 8, j); PROF(2, tid == 0 && j, 9 + ps * 8); }
        wg_wait<1>();
        keep(s);
        mbar_arrive_cl(rempty, ODD ? 24 : 8, !last);
        PROF(4, tid == 0 && ps == 1, 51 + j);
      };
      uint32_t pa[32], pb[32];
#pragma unroll 1
      for (int j = 0; j < 8; j += 2) {
        step(std::false_type{}, j, pa, pb);
        step(std::true_type{}, j + 1, pb, pa);
      }
      {
        const float i0 = inv_quad_sum(l0), i1 = inv_quad_sum(l1);
        wg_wait<0>();
        keep(o);
        mbar_arrive_cl(rempty, 24);
        store_chunk<0>(o, i0, i1, qw + unit_of(qt, 2) + frag_offset(warp));
        store_chunk<1>(o, i0, i1, qw + unit_of(qt, 3) + frag_offset(warp));
        fence_async_smem();
        mbar_arrive(bar_ofull + wg * 8);
      }
      PROF(2, tid == 0, 10 + ps * 8);
    }

    const int ln = fresh_lane(), g = ln >> 2, tq = ln & 3, ct = warp * 32 + ln;
    const bool lane0 = ln == 0;
    const int lrow0 = warp * 16 + g;
    const int grow0 = rb * 128 + lrow0;
    const uint32_t res = base + OFF_RES, trow = res + wg * 8192 + frag_offset(warp);
    uint32_t xr[32];
    {
      const uint64_t da = make_desc(base + wg * 8192, 16, 1024), db = make_desc(base, 8192, 1024);
      constexpr int U = UNIT / 16;
#define HALF_STAGE(acc, xu, wu) _Pragma("unroll") for (int kk = 0; kk < 4; kk++) mma_ss<1>(acc, da + (xu) * U + kk * 2, db + (wu) * U + kk * 128, 1)
      PROF(10, ct == PT, 19); STAMP(0);
      cluster_arrive();
      mbar_wait(gfull, 1);
      mbar_wait(gfull + 8, 1);
      bar_sync(2 + wg, 256);
      wg_fence();
      HALF_STAGE(o, 6, 8);
      HALF_STAGE(o, 9, 11);
      wg_commit();
      STAMP(16);
      mbar_wait(gfull + 16, 1);
      STAMP(17);
      wg_fence();
      HALF_STAGE(o, 12, 1);
      wg_commit();
      bar_arrive(3 - wg, 256);
      mbar_wait(bar_par, 0);
      uint32_t* xo = g_xch + ((size_t)b * 8 * 256 + ct) * 4;
      const uint32_t* xi = g_xch + ((size_t)(b ^ 2) * 8 * 256 + ct) * 4;
      const uint32_t par1 = (~lds1(par + PAR_CONST + 4) & 1) << 16;
      wg_wait<0>();
      keep(o);
      mbar_arrive_pred(bar_ring, lane0);
      PROF(8, ct == PT, 20); STAMP(1);
#define SEND(i) st_b128(xo + (i) * 1024, (pack_bf(o[8 * (i)], o[8 * (i) + 1]) & ~0x10000u) | par1, pack_bf(o[8 * (i) + 2], o[8 * (i) + 3]), \
                        pack_bf(o[8 * (i) + 4], o[8 * (i) + 5]), pack_bf(o[8 * (i) + 6], o[8 * (i) + 7]))
#pragma unroll
      for (int i = 0; i < NS1; i++) SEND(i);
      PROF(8, ct == PT, 21); STAMP(2);
      bar_sync(2 + wg, 256);
      wg_fence();
      HALF_STAGE(s, 6, 7);
      HALF_STAGE(s, 9, 10);
      HALF_STAGE(s, 12, 0);
      wg_commit();
      bar_arrive(3 - wg, 256);
      STAMP(18);
      mbar_wait(gfull + 24, 1);
#pragma unroll
      for (int i = NS1; i < 8; i++) SEND(i);
      uint4 v[8];
#pragma unroll
      for (int i = 0; i < 4; i++) v[i] = ld_b128(xi + i * 1024);
      STAMP(19);
      mbar_wait(bar_rx, 0);
      wg_wait<0>();
      mbar_arrive_pred(bar_ring + 8, lane0);
      bar_sync(2 + wg, 256);
      STAMP(20);
#pragma unroll
      for (int i = 4; i < 8; i++) v[i] = ld_b128(xi + i * 1024);
      mbar_wait(bar_xres, 0);
      wg_fence();
      HALF_STAGE(s, 13, 2);
      HALF_STAGE(s, 8, 3);
      wg_commit();
      bar_arrive(3 - wg, 256);
      STAMP(21);
      wg_wait<0>();
      keep(s);
      mbar_arrive_pred(bar_ring + 16, lane0);
      PROF(10, ct == PT, 23); STAMP(4);
#pragma unroll
      for (int i = 0; i < 16; i += 2) ldmatrix4((trow ^ ((i & 7) << 4)) + (i >> 3) * 16384, xr[2 * i], xr[2 * i + 1], xr[2 * i + 2], xr[2 * i + 3]);
      {
        uint32_t n = 0;
        bool ok;
        do {
          ok = true;
#pragma unroll
          for (int i = 0; i < 8; i++)
            if ((v[i].x & 0x10000u) != par1) { v[i] = ld_b128(xi + i * 1024); ok = false; }
          watchdog(n);
        } while (!ok);
      }
      __syncwarp();
      PROF(8, ct == PT, 22); STAMP(3);
      float ds[4] = {0.f, 0.f, 0.f, 0.f}, dl[4] = {0.f, 0.f, 0.f, 0.f}, q0[4] = {0.f, 0.f, 0.f, 0.f}, q1[4] = {0.f, 0.f, 0.f, 0.f};
#pragma unroll
      for (int i = 0; i < 8; i++) {
        const uint32_t ga0 = lds1(par + PAR_T2 + i * 128 + tq * 16 + 12), ga1 = lds1(par + PAR_T2 + i * 128 + 64 + tq * 16 + 12);
        const uint4 bw = lds4(par + PAR_T1 + i * 64 + tq * 16);
        const uint32_t u0 = hfma2(ga0, hadd2(pack_bf(s[8 * i], s[8 * i + 1]), v[i].x & ~0x10000u), xr[4 * i]);
        const uint32_t u1 = hfma2(ga0, hadd2(pack_bf(s[8 * i + 2], s[8 * i + 3]), v[i].y), xr[4 * i + 1]);
        const uint32_t u2 = hfma2(ga1, hadd2(pack_bf(s[8 * i + 4], s[8 * i + 5]), v[i].z), xr[4 * i + 2]);
        const uint32_t u3 = hfma2(ga1, hadd2(pack_bf(s[8 * i + 6], s[8 * i + 7]), v[i].w), xr[4 * i + 3]);
        xr[4 * i] = u0; xr[4 * i + 1] = u1; xr[4 * i + 2] = u2; xr[4 * i + 3] = u3;
        mma16816(ds, u0, u1, u2, u3, (g & 1) ? bw.x : 0x3f803f80u, (g & 1) ? bw.y : 0x3f803f80u);
        mma16816(dl, u0, u1, u2, u3, bw.z, bw.w);
        mma16816(q0, u0, u1, u2, u3, u0, u2);
        mma16816(q1, u0, u1, u2, u3, u1, u3);
      }
      if (tq == (g >> 1)) {
        uint32_t* dst = g_stats + ((size_t)cj * SEQ + grow0) * 4;
        st_b128(dst, __float_as_uint(ds[0]), __float_as_uint((g & 1) ? q0[1] : q0[0]), __float_as_uint(ds[1] + dl[1]), tag);
        st_b128(dst + 32, __float_as_uint(ds[2]), __float_as_uint((g & 1) ? q1[3] : q1[2]), __float_as_uint(ds[3] + dl[3]), tag);
      }
    }
    PROF(8, ct == PT, 29); STAMP(5);
    uint32_t mm, ih, il;
    float rbest;
    uint32_t wf[128];
    const uint32_t frow = (ln & 7) + (ln >> 4) * 8;
    const uint32_t wfo = base + (warp & 1) * 8192 + frow * 64 + ((((ln >> 3) & 1) ^ ((frow >> 1) & 3)) << 4);
#define LOAD_WF(m) _Pragma("unroll") for (int f = 0; f < 16; f++) {                                                   \
      const int r = ((f >> 1) * 4 + (m) * 2 + (f & 1)) * 4;                                                           \
      ldmatrix4t(((wfo + unit_of((m) ? FT_U : FT_G, warp >> 1)) ^ ((f & 1) * 32)) + (f >> 1) * 1024, wf[r], wf[r + 1], wf[r + 2], wf[r + 3]); \
    }
    bool early;
    {
      const uint32_t* sp = g_stats + ((size_t)(tq >> 1) * 4 * SEQ + grow0 + (tq & 1) * 8) * 4;
      uint4 v0 = ld_b128(sp), v1 = ld_b128(sp + SEQ * 4), v2 = ld_b128(sp + SEQ * 8), v3 = ld_b128(sp + SEQ * 12);
#pragma unroll
      for (int i = 0; i < 16; i += 2) stmatrix4((trow ^ ((i & 7) << 4)) + (i >> 3) * 16384, xr[2 * i], xr[2 * i + 1], xr[2 * i + 2], xr[2 * i + 3]);
      early = __all_sync(0xffffffffu, b >= NFFN || mbar_test(bar_box + (warp >> 1) * 8, 0));
      LOAD_WF(0);
      __syncwarp();
      mbar_arrive_pred(bar_gate, lane0 && early);
      const uint4 cst = lds4(par + PAR_CONST);
      const float A1 = __uint_as_float(cst.x), A2 = __uint_as_float(cst.z);
      uint32_t n = 0;
      while (v0.w != tag || v1.w != tag || v2.w != tag || v3.w != tag) {
        if (v0.w != tag) v0 = ld_b128(sp);
        if (v1.w != tag) v1 = ld_b128(sp + SEQ * 4);
        if (v2.w != tag) v2 = ld_b128(sp + SEQ * 8);
        if (v3.w != tag) v3 = ld_b128(sp + SEQ * 12);
        watchdog(n);
      }
      __syncwarp();
      PROF(8, ct == PT, 30); STAMP(6);
      float su = (__uint_as_float(v0.x) + __uint_as_float(v1.x)) + (__uint_as_float(v2.x) + __uint_as_float(v3.x));
      float sq = (__uint_as_float(v0.y) + __uint_as_float(v1.y)) + (__uint_as_float(v2.y) + __uint_as_float(v3.y));
      float dt = (__uint_as_float(v0.z) + __uint_as_float(v1.z)) + (__uint_as_float(v2.z) + __uint_as_float(v3.z));
      su += __shfl_xor_sync(0xffffffffu, su, 2); sq += __shfl_xor_sync(0xffffffffu, sq, 2); dt += __shfl_xor_sync(0xffffffffu, dt, 2);
      const float m = su * (1.f / DM);
      float mb, sd;
      ln_scalars(m, fmaxf(sq * (1.f / DM) - m * m, 0.f), mb, sd);
      const float inv = rcp(sd);
      rbest = (dt - mb * A1) * inv + A2;
      mm = pack_bf(mb, mb);
      ih = pack_bf(inv, inv);
      const float lo = inv - bf_lo(ih);
      il = pack_bf(lo, lo);
    }
    int ibest;
    {
      const uint32_t bits = __float_as_uint(rbest);
      const uint32_t key = (((int)bits < 0 ? ~bits : bits | 0x80000000u) & ~0x1ffu) | ((127 - lrow0 - (tq & 1) * 8) << 2) | tag;
      sts1(par + PAR_RED + warp * 4, __reduce_max_sync(0xffffffffu, key));
      PROF(8, ct == PT, 38); STAMP(7);
      bar_sync(1, 256);
      const uint4 ka = lds4(par + PAR_RED), kb = lds4(par + PAR_RED + 16);
      const uint32_t k2 = max(max(max(ka.x, ka.y), max(ka.z, ka.w)), max(max(kb.x, kb.y), max(kb.z, kb.w)));
      if (ct < 16) st_relaxed(g_cand + (cj * 16 + ct) * 32 + rb, k2);
      ibest = 127 - ((k2 >> 2) & 127);
    }
    PROF(8, ct == PT, 39); STAMP(8);
    if ((ibest >> 4) == warp) {
      const int src = (ibest & 7) * 4 + ((ibest >> 3) & 1), ch = g * 2;
      const uint32_t cm = __shfl_sync(0xffffffffu, mm, src), ch_ = __shfl_sync(0xffffffffu, ih, src), cl = __shfl_sync(0xffffffffu, il, src);
      const uint32_t xa = res + (ch >> 3) * 16384 + ibest * 128 + (((ch & 7) ^ (ibest & 7)) << 4) + tq * 4;
      const uint32_t x0 = lds1(xa), x1 = lds1(xa ^ 16);
      const uint2 p0 = lds2(par + PAR_T2 + ch * 64 + tq * 16), p1 = lds2(par + PAR_T2 + ch * 64 + 64 + tq * 16);
      uint32_t* dst = g_row + rb * 2 * DM + cj * 128 + ln * 4;
      st_pairs(dst, ln_mod(x0, cm, ch_, cl, p0.x, p0.y), ln_mod(x1, cm, ch_, cl, p1.x, p1.y), tag);
      st_pairs(dst + DM, x0, x1, tag);
      __syncwarp();
    }
    PROF(8, ct == PT, 37); STAMP(9);
    uint32_t wd[64];
    const uint32_t wda = base + unit_of(FT_D, warp >> 1) + (warp & 1) * 8192 + frow * 128 + ((((ln >> 3) & 1) ^ (ln & 7)) << 4);
#define LOAD_WD(f) ldmatrix4t((wda ^ ((((f) >> 1) & 3) * 32)) + ((f) >> 3) * 4096 + ((f) & 1) * 2048, wd[4 * (f)], wd[4 * (f) + 1], wd[4 * (f) + 2], wd[4 * (f) + 3])
    if (!early) {
      mbar_wait(bar_box + (warp >> 1) * 8, 0);
      LOAD_WF(0);
      __syncwarp();
      mbar_arrive_pred(bar_gate, lane0);
    }
    if (b < NFFN) {
      const uint32_t own = base + unit_of(FT_G, warp >> 1) + (warp & 1) * 8192;
      mbar_wait(bar_box + (4 + (warp >> 1)) * 8, 0);
      LOAD_WF(1);
      uint32_t* const ydst = g_ypart + ((size_t)(warp * 16 + tq * 2) * NFFN + b) * 8 + g;
      PROF(8, ct == PT, 31); STAMP(10);
      mbar_wait(bar_box + (8 + (warp >> 1)) * 8, 0);
#pragma unroll
      for (int f = 0; f < WDE; f++) LOAD_WD(f);
      STAMP(11);
      mbar_wait(bar_sel, 0);
      PROF(8, ct == PT, 33); STAMP(12);
      float d[8][4];
#pragma unroll
      for (int i = 0; i < 4; i++) { d[i][0] = 0.f; d[i][1] = 0.f; d[i][2] = 0.f; d[i][3] = 0.f; }
#pragma unroll
      for (int ks = 0; ks < 8; ks++) {
        const uint2 hb = lds2(own + 256 + ks * 32 + tq * 8);
#pragma unroll
        for (int mt = 0; mt < 4; mt++) {
          const int r = ks * 16 + mt * 4;
          mma16816(d[mt], wf[r], wf[r + 1], wf[r + 2], wf[r + 3], hb.x, hb.y);
        }
      }
      sts2(own + (tq * 8 + g) * 8, __float_as_uint((tq & 2) ? ((tq & 1) ? d[1][2] : d[1][0]) : ((tq & 1) ? d[0][2] : d[0][0])),
           __float_as_uint((tq & 2) ? ((tq & 1) ? d[3][2] : d[3][0]) : ((tq & 1) ? d[2][2] : d[2][0])));
      bar_sync(1, 256);
      uint32_t ab[4];
      {
        float G = 0.f, U = 0.f;
        uint2 pv[8];
#pragma unroll
        for (int w8 = 0; w8 < 8; w8++) pv[w8] = lds2(base + ln * 8 + ((FT_G >> (w8 >> 1) * 4) & 15) * UNIT + (w8 & 1) * 8192);
#pragma unroll
        for (int w8 = 0; w8 < 8; w8 += 2) {
          G += __uint_as_float(pv[w8].x) + __uint_as_float(pv[w8 + 1].x);
          U += __uint_as_float(pv[w8].y) + __uint_as_float(pv[w8 + 1].y);
        }
#pragma unroll
        for (int f = WDE; f < 16; f++) LOAD_WD(f);
        const float act = rbf(silu_f(rbf(G))) * rbf(U);
        const uint32_t pk = pack_bf(act, __shfl_down_sync(0xffffffffu, act, 1));
#pragma unroll
        for (int i = 0; i < 4; i++) ab[i] = __shfl_sync(0xffffffffu, pk, i * 8 + tq * 2);
      }
      PROF(8, ct == PT, 34); STAMP(13);
#pragma unroll
      for (int mt = 0; mt < 8; mt++) {
        d[mt][0] = 0.f; d[mt][1] = 0.f; d[mt][2] = 0.f; d[mt][3] = 0.f;
        mma16816(d[mt], wd[mt * 8], wd[mt * 8 + 1], wd[mt * 8 + 2], wd[mt * 8 + 3], ab[0], ab[1]);
        mma16816(d[mt], wd[mt * 8 + 4], wd[mt * 8 + 5], wd[mt * 8 + 6], wd[mt * 8 + 7], ab[2], ab[3]);
      }
#pragma unroll
      for (int i = 0; i < 4; i++) {
        const int m4 = (i >> 1) * 4, e = (i & 1) * 2;
        const float y = (tq & 2) ? ((tq & 1) ? d[m4 + 3][e] : d[m4 + 2][e]) : ((tq & 1) ? d[m4 + 1][e] : d[m4][e]);
        st_relaxed(ydst + (m4 * 2 + (i & 1)) * NFFN * 8, tagf(y, tag));
      }
      PROF(8, ct == PT, 35); STAMP(14);
    }
    mbar_wait(bar_sel, 0);
    mbar_arrive_pred(bar_win, ct == 0);
    const int iwin = lds1(par + PAR_CONST + 60) & 0x7ff;
    {
      const uint32_t mm0 = __shfl_sync(0xffffffffu, mm, ln & ~1), mm1 = __shfl_sync(0xffffffffu, mm, ln | 1);
      const uint32_t ih0 = __shfl_sync(0xffffffffu, ih, ln & ~1), ih1 = __shfl_sync(0xffffffffu, ih, ln | 1);
      const uint32_t il0 = __shfl_sync(0xffffffffu, il, ln & ~1), il1 = __shfl_sync(0xffffffffu, il, ln | 1);
      const bool mine = (iwin >> 4) == rb * 8 + warp;
#pragma unroll 1
      for (int hf = 0; hf < 2; hf++) {
        uint32_t x[16];
#pragma unroll
        for (int i = 0; i < 8; i += 2) ldmatrix4((trow ^ (i << 4)) + hf * 16384, x[2 * i], x[2 * i + 1], x[2 * i + 2], x[2 * i + 3]);
#pragma unroll
        for (int i = 0; i < 8; i++) {
          const uint4 pv = lds4(par + PAR_T2 + (hf * 8 + i) * 64 + tq * 16);
          x[2 * i] = hadd2(x[2 * i], hmul2(pv.z, ln_mod(x[2 * i], mm0, ih0, il0, pv.x, pv.y)));
          x[2 * i + 1] = hadd2(x[2 * i + 1], hmul2(pv.z, ln_mod(x[2 * i + 1], mm1, ih1, il1, pv.x, pv.y)));
        }
        if (mine) {
          uint32_t* dst = reinterpret_cast<uint32_t*>(P.out + (size_t)grow0 * DM + cj * 128 + hf * 64) + tq;
#pragma unroll
          for (int i = 0; i < 8; i++) {
            if (grow0 != iwin) dst[i * 4] = x[2 * i];
            if (grow0 + 8 != iwin) dst[i * 4 + 4 * DM] = x[2 * i + 1];
          }
        } else {
#pragma unroll
          for (int i = 0; i < 8; i += 2) stmatrix4((trow ^ (i << 4)) + hf * 16384, x[2 * i], x[2 * i + 1], x[2 * i + 2], x[2 * i + 3]);
          fence_async_smem();
          __syncwarp();
          if (elect_one()) {
            tma2d_store(&maps.out, res + hf * 16384 + warp * 2048, cj * 128 + hf * 64, rb * 128 + warp * 16);
            asm volatile("cp.async.bulk.commit_group;" ::: "memory");
          }
        }
      }
      asm volatile("cp.async.bulk.wait_group.read 0;" ::: "memory");
    }
    PROF(8, ct == PT, 11); STAMP(15);
    cluster_wait();
  }
}

typedef CUresult (*EncodeFn)(CUtensorMap*, CUtensorMapDataType, cuuint32_t, void*, const cuuint64_t*, const cuuint64_t*,
                             const cuuint32_t*, const cuuint32_t*, CUtensorMapInterleave, CUtensorMapSwizzle,
                             CUtensorMapL2promotion, CUtensorMapFloatOOBfill);

void map2d(EncodeFn enc, CUtensorMap* m, const void* p, uint64_t rows, uint64_t cols, uint32_t brows) {
  cuuint64_t dims[2] = {cols, rows}, strides[1] = {cols * 2};
  cuuint32_t box[2] = {64, brows}, es[2] = {1, 1};
  enc(m, CU_TENSOR_MAP_DATA_TYPE_BFLOAT16, 2, const_cast<void*>(p), dims, strides, box, es, CU_TENSOR_MAP_INTERLEAVE_NONE,
      CU_TENSOR_MAP_SWIZZLE_128B, CU_TENSOR_MAP_L2_PROMOTION_L2_256B, CU_TENSOR_MAP_FLOAT_OOB_FILL_NONE);
}
void map2d_narrow(EncodeFn enc, CUtensorMap* m, const void* p, uint64_t rows, uint64_t cols) {
  cuuint64_t dims[2] = {cols, rows}, strides[1] = {cols * 2};
  cuuint32_t box[2] = {32, 256}, es[2] = {1, 1};
  enc(m, CU_TENSOR_MAP_DATA_TYPE_BFLOAT16, 2, const_cast<void*>(p), dims, strides, box, es, CU_TENSOR_MAP_INTERLEAVE_NONE,
      CU_TENSOR_MAP_SWIZZLE_64B, CU_TENSOR_MAP_L2_PROMOTION_L2_64B, CU_TENSOR_MAP_FLOAT_OOB_FILL_NONE);
}
void map3d(EncodeFn enc, CUtensorMap* m, const void* p, uint64_t rows, uint64_t cols, uint32_t brows, uint32_t nch) {
  cuuint64_t dims[3] = {64, rows, cols / 64}, strides[2] = {cols * 2, 128};
  cuuint32_t box[3] = {64, brows, nch}, es[3] = {1, 1, 1};
  enc(m, CU_TENSOR_MAP_DATA_TYPE_BFLOAT16, 3, const_cast<void*>(p), dims, strides, box, es, CU_TENSOR_MAP_INTERLEAVE_NONE,
      CU_TENSOR_MAP_SWIZZLE_128B, CU_TENSOR_MAP_L2_PROMOTION_L2_256B, CU_TENSOR_MAP_FLOAT_OOB_FILL_NONE);
}

}

extern "C" void kernel_launch(void* const* d_in, const int* in_sizes, int n_in, void* d_out, int out_size) {
  (void)in_sizes; (void)n_in; (void)out_size;
  static EncodeFn enc = nullptr;
  if (!enc) {
    void* fn = nullptr;
    cudaDriverEntryPointQueryResult st;
    cudaGetDriverEntryPoint("cuTensorMapEncodeTiled", &fn, cudaEnableDefault, &st);
    enc = (EncodeFn)fn;
    cudaFuncSetAttribute(fused_kernel, cudaFuncAttributeMaxDynamicSharedMemorySize, SMEM_BYTES);
  }
  Maps maps;
  map2d(enc, &maps.x, d_in[0], SEQ, DM, 128);
  map2d(enc, &maps.out, d_out, SEQ, DM, 16);
  map3d(enc, &maps.wq, d_in[3], DM, NQ, 64, 2);
  map3d(enc, &maps.k, d_in[1], 4 * SK, 128, 128, 1);
  map3d(enc, &maps.v, d_in[2], 4 * SK, 128, 128, 1);
  map3d(enc, &maps.wo, d_in[4], NQ, DM, 64, 2);
  map2d_narrow(enc, &maps.wg, d_in[7], DM, FF);
  map2d_narrow(enc, &maps.wu, d_in[8], DM, FF);
  map3d(enc, &maps.wd, d_in[9], FF, DM, 32, 4);
  map2d_narrow(enc, &maps.wm, d_in[11], DM, NMOD);
  Ptrs p;
  p.x = (const __nv_bfloat16*)d_in[0];
  p.w_r = (const __nv_bfloat16*)d_in[6];
  p.w_gate = (const __nv_bfloat16*)d_in[7];
  p.w_up = (const __nv_bfloat16*)d_in[8];
  p.w_down = (const __nv_bfloat16*)d_in[9];
  p.c = (const __nv_bfloat16*)d_in[10];
  p.w_mod = (const __nv_bfloat16*)d_in[11];
  p.out = (__nv_bfloat16*)d_out;
  fused_kernel<<<NMAIN + NHELP, 384, SMEM_BYTES>>>(maps, p);
}
```

```cpp
#include <cuda_runtime.h>
#include <cuda_bf16.h>
#include <cuda.h>
#include <stdint.h>
#include <type_traits>

#define HD 1
#define HDX 2
#define XF 4
#define XE 32
#define XR 0
#define PF2 1
#define PF2T 4
#define NRS 6
#define FPACE 3
#define GOST 20
#define WB 2
#define WN 24
#define RES0 17
#define RES1 20
#define HU 32
#define NS1 6
#define PD0 40
#define PG0 31
#define PSL 0
#define CWM 0
#define WDE 16
#define VREL 7
#define E0 3

namespace {

constexpr int SEQ = 2048, DM = 1024, NQ = 4096, SK = 2048, WIN = 512, FF = 3584, NMOD = 6144;
constexpr int NMAIN = 128, NHELP = 4, NFFN = 112;
constexpr int NSLOT = 4, SLOT_BYTES = 32768, UNIT = 16384, GST_BYTES = 3 * UNIT;
constexpr uint32_t XT0 = 0x9630, XT1 = 0x54DC, XT2 = 0xDC96;
constexpr uint32_t WT0 = 0xA741, WT1 = 0x720A, WT2 = 0x20A7;
constexpr uint32_t AT0 = 0x7420, AT1 = 0x2C0A;
constexpr uint32_t QT = 0x549696DC;
constexpr int OFF_STAGE = 12 * UNIT;
constexpr uint32_t FT_G = 0x761B, FT_U = 0x0CA9, FT_D = 0x382D;
constexpr int OFF_RES = 4 * UNIT;
constexpr int OFF_PAR = 14 * UNIT;
constexpr int OFF_BAR = OFF_PAR + 2048 + 512;
constexpr int SMEM_BYTES = OFF_BAR + 512;
static_assert(SMEM_BYTES <= 232448, "smem");

constexpr int PAR_T1 = 0;
constexpr int PAR_T2 = 512;
constexpr int PAR_CONST = 1536;
constexpr int PAR_RED = 1600;
constexpr int PAR_SINK = 2176;

struct Maps {
  CUtensorMap x, wq, k, v, wo, wg, wu, wd, wm, out;
};
struct Ptrs {
  const __nv_bfloat16 *x, *w_r, *c, *w_mod, *w_gate, *w_up, *w_down;
  __nv_bfloat16* out;
};

__device__ __align__(1024) uint8_t g_act[16 * 80 * UNIT];
__device__ __align__(128) uint32_t g_mod[NMOD];
__device__ __align__(128) uint32_t g_modp[2 * 2 * DM];
__device__ __align__(128) uint32_t g_ln1[SEQ * 4];
__device__ __align__(128) uint32_t g_cnt_h[16 * 32];
__device__ __align__(128) uint32_t g_cnt_o[128 * 32];
__device__ __align__(128) uint32_t g_xch[NMAIN * 8 * 256 * 4];
__device__ __align__(128) uint32_t g_stats[8 * SEQ * 4];
__device__ __align__(128) uint32_t g_cand[32];
__device__ __align__(128) uint32_t g_row[16 * 2 * DM];
__device__ __align__(128) uint32_t g_ypart[NMAIN * NFFN * 8];
__device__ uint32_t g_epoch;

__device__ __forceinline__ uint32_t fresh_lane() { uint32_t l; asm volatile("mov.u32 %0, %%laneid;" : "=r"(l)); return l; }
__device__ __forceinline__ uint32_t frag_offset(int warp) {
  const uint32_t l = fresh_lane();
  return ((warp & 3) * 16 + (l & 15)) * 128 + (((l >> 4) ^ (l & 7)) << 4);
}
__device__ __forceinline__ bool elect_one() {
  uint32_t p;
  asm volatile("{ .reg .pred q; elect.sync _|q, 0xffffffff; selp.u32 %0, 1, 0, q; }" : "=r"(p));
  return p;
}
__device__ __forceinline__ uint32_t smem_u32(const void* p) { return (uint32_t)__cvta_generic_to_shared(p); }
__device__ __forceinline__ void mbar_init(uint32_t bar, uint32_t cnt) {
  asm volatile("mbarrier.init.shared::cta.b64 [%0], %1;" ::"r"(bar), "r"(cnt) : "memory");
}
__device__ __forceinline__ void mbar_expect_tx(uint32_t bar, uint32_t bytes) {
  asm volatile("mbarrier.arrive.expect_tx.shared::cta.b64 _, [%0], %1;" ::"r"(bar), "r"(bytes) : "memory");
}
__device__ __forceinline__ void mbar_arrive(uint32_t bar) {
  asm volatile("mbarrier.arrive.shared::cta.b64 _, [%0];" ::"r"(bar) : "memory");
}
__device__ __forceinline__ void mbar_arrive_pred(uint32_t bar, bool p) {
  asm volatile("{ .reg .pred p; setp.ne.b32 p, %1, 0; @p mbarrier.arrive.shared::cta.b64 _, [%0]; }" ::"r"(bar), "r"((int)p) : "memory");
}
__device__ __forceinline__ void mbar_arrive_cl(uint32_t bar, uint32_t off, bool p = true) {
  asm volatile("{ .reg .pred p, q; .reg .b32 a; setp.ne.b32 q, %2, 0; setp.ne.and.b32 p, %0, 0, q; add.u32 a, %0, %1; @p mbarrier.arrive.shared::cluster.b64 _, [a]; }"
               ::"r"(bar), "r"(off), "r"((int)p) : "memory");
}
__device__ __forceinline__ uint32_t mapa(uint32_t addr, uint32_t cta) {
  uint32_t r; asm("mapa.shared::cluster.u32 %0, %1, %2;" : "=r"(r) : "r"(addr), "r"(cta)); return r;
}
__device__ __forceinline__ void cluster_arrive() { asm volatile("barrier.cluster.arrive.relaxed.aligned;" ::: "memory"); }
__device__ __forceinline__ void cluster_wait() { asm volatile("barrier.cluster.wait.aligned;" ::: "memory"); }
__device__ __forceinline__ void watchdog(uint32_t& n) {
}
__device__ __forceinline__ void mbar_wait(uint32_t bar, uint32_t parity) {
  asm volatile("{\n.reg .pred p;\nWAIT_%=:\nmbarrier.try_wait.parity.shared::cta.b64 p, [%0], %1;\n@!p bra WAIT_%=;\n}" ::"r"(bar), "r"(parity) : "memory");
}
__device__ __forceinline__ bool mbar_test(uint32_t bar, uint32_t parity) {
  uint32_t ok;
  asm volatile("{\n.reg .pred p;\nmbarrier.test_wait.parity.shared::cta.b64 p, [%1], %2;\nselp.u32 %0, 1, 0, p;\n}" : "=r"(ok) : "r"(bar), "r"(parity) : "memory");
  return ok;
}
__device__ __forceinline__ uint64_t l2_stream() {
  uint64_t f; asm("createpolicy.fractional.L2::evict_first.b64 %0, 1.0;" : "=l"(f)); return f;
}
__device__ __forceinline__ void tma2d(uint32_t dst, const CUtensorMap* m, int c0, int c1, uint32_t bar) {
  asm volatile("cp.async.bulk.tensor.2d.shared::cluster.global.mbarrier::complete_tx::bytes.L2::cache_hint [%0], [%1, {%3, %4}], [%2], %5;"
               ::"r"(dst), "l"(m), "r"(bar), "r"(c0), "r"(c1), "l"(l2_stream()) : "memory");
}
__device__ __forceinline__ void tma3d_prefetch(const CUtensorMap* m, int c0, int c1, int c2) {
  asm volatile("cp.async.bulk.prefetch.tensor.3d.L2.global.tile [%0, {%1, %2, %3}];" ::"l"(m), "r"(c0), "r"(c1), "r"(c2) : "memory");
}
__device__ __forceinline__ void bulk_load(uint32_t dst, const void* src, uint32_t bytes, uint32_t bar) {
  asm volatile("cp.async.bulk.shared::cluster.global.mbarrier::complete_tx::bytes [%0], [%1], %2, [%3];" ::"r"(dst), "l"(src), "r"(bytes), "r"(bar) : "memory");
}
__device__ __forceinline__ void bulk_load_stream(uint32_t dst, const void* src, uint32_t bytes, uint32_t bar) {
  asm volatile("cp.async.bulk.shared::cluster.global.mbarrier::complete_tx::bytes.L2::cache_hint [%0], [%1], %2, [%3], %4;"
               ::"r"(dst), "l"(src), "r"(bytes), "r"(bar), "l"(l2_stream()) : "memory");
}
__device__ __forceinline__ void tma2d_store(const CUtensorMap* m, uint32_t src, int c0, int c1) {
  asm volatile("cp.async.bulk.tensor.2d.global.shared::cta.bulk_group [%0, {%2, %3}], [%1];" ::"l"(m), "r"(src), "r"(c0), "r"(c1) : "memory");
}
__device__ __forceinline__ void bulk_store(void* dst, uint32_t src, uint32_t bytes) {
  asm volatile("cp.async.bulk.global.shared::cta.bulk_group [%0], [%1], %2;" ::"l"(dst), "r"(src), "r"(bytes) : "memory");
}
__device__ __forceinline__ uint32_t unit_of(uint32_t table, uint32_t i) { return ((table >> (i * 4)) & 15) * UNIT; }
__device__ __forceinline__ void tma3d(uint32_t dst, const CUtensorMap* m, int c0, int c1, int c2, uint32_t bar) {
  asm volatile("cp.async.bulk.tensor.3d.shared::cluster.global.mbarrier::complete_tx::bytes.L2::cache_hint [%0], [%1, {%3, %4, %5}], [%2], %6;"
               ::"r"(dst), "l"(m), "r"(bar), "r"(c0), "r"(c1), "r"(c2), "l"(l2_stream()) : "memory");
}
template <bool STREAM>
__device__ __forceinline__ void tma3d_mc(uint32_t dst, const CUtensorMap* m, int c0, int c1, int c2, uint32_t bar) {
  if (STREAM)
    asm volatile("cp.async.bulk.tensor.3d.shared::cluster.global.mbarrier::complete_tx::bytes.multicast::cluster.L2::cache_hint [%0], [%1, {%3, %4, %5}], [%2], %6, %7;"
                 ::"r"(dst), "l"(m), "r"(bar), "r"(c0), "r"(c1), "r"(c2), "h"((uint16_t)3), "l"(l2_stream()) : "memory");
  else
    asm volatile("cp.async.bulk.tensor.3d.shared::cluster.global.mbarrier::complete_tx::bytes.multicast::cluster [%0], [%1, {%3, %4, %5}], [%2], %6;"
                 ::"r"(dst), "l"(m), "r"(bar), "r"(c0), "r"(c1), "r"(c2), "h"((uint16_t)3) : "memory");
}
__device__ __forceinline__ void prefetch_map(const CUtensorMap* m) {
  asm volatile("prefetch.tensormap [%0];" ::"l"(m) : "memory");
}
__device__ __forceinline__ void fence_async() { asm volatile("fence.proxy.async.global;" ::: "memory"); }
__device__ __forceinline__ void fence_async_smem() { asm volatile("fence.proxy.async.shared::cta;" ::: "memory"); }
__device__ __forceinline__ void bar_sync(int id, int n) { asm volatile("bar.sync %0, %1;" ::"r"(id), "r"(n) : "memory"); }
__device__ __forceinline__ void bar_arrive(int id, int n) { asm volatile("bar.arrive %0, %1;" ::"r"(id), "r"(n) : "memory"); }
__device__ __forceinline__ void wg_fence() { asm volatile("wgmma.fence.sync.aligned;" ::: "memory"); }
__device__ __forceinline__ void wg_commit() { asm volatile("wgmma.commit_group.sync.aligned;" ::: "memory"); }
template <int N> __device__ __forceinline__ void wg_wait() { asm volatile("wgmma.wait_group.sync.aligned %0;" ::"n"(N) : "memory"); }
__device__ __forceinline__ uint64_t make_desc(uint32_t addr, uint32_t lbo, uint32_t sbo) {
  return (uint64_t)((addr & 0x3FFFF) >> 4) | ((uint64_t)(lbo >> 4) << 16) | ((uint64_t)(sbo >> 4) << 32) | (1ull << 62);
}
__device__ __forceinline__ uint32_t ld_relaxed(const uint32_t* p) {
  uint32_t v; asm volatile("ld.relaxed.gpu.global.u32 %0, [%1];" : "=r"(v) : "l"(p) : "memory"); return v;
}
__device__ __forceinline__ uint32_t ld_acquire(const uint32_t* p) {
  uint32_t v; asm volatile("ld.acquire.gpu.global.u32 %0, [%1];" : "=r"(v) : "l"(p) : "memory"); return v;
}
__device__ __forceinline__ uint4 ld_relaxed4(const uint32_t* p) {
  uint4 v; asm volatile("ld.relaxed.gpu.global.v4.u32 {%0,%1,%2,%3}, [%4];" : "=r"(v.x), "=r"(v.y), "=r"(v.z), "=r"(v.w) : "l"(p) : "memory"); return v;
}
__device__ __forceinline__ uint2 ld_relaxed2(const uint32_t* p) {
  uint2 v; asm volatile("ld.relaxed.gpu.global.v2.u32 {%0,%1}, [%2];" : "=r"(v.x), "=r"(v.y) : "l"(p) : "memory"); return v;
}
__device__ __forceinline__ void st_relaxed(uint32_t* p, uint32_t v) {
  asm volatile("st.relaxed.gpu.global.u32 [%0], %1;" ::"l"(p), "r"(v) : "memory");
}
__device__ __forceinline__ void st_relaxed2(uint32_t* p, uint32_t a, uint32_t b) {
  asm volatile("st.relaxed.gpu.global.v2.u32 [%0], {%1,%2};" ::"l"(p), "r"(a), "r"(b) : "memory");
}
__device__ __forceinline__ void st_relaxed4(uint32_t* p, uint32_t a, uint32_t b, uint32_t c, uint32_t d) {
  asm volatile("st.relaxed.gpu.global.v4.u32 [%0], {%1,%2,%3,%4};" ::"l"(p), "r"(a), "r"(b), "r"(c), "r"(d) : "memory");
}
__device__ __forceinline__ void st_b128(uint32_t* p, uint32_t a, uint32_t b, uint32_t c, uint32_t d) {
  asm volatile("{ .reg .b64 u, v; .reg .b128 w; mov.b64 u, {%1, %2}; mov.b64 v, {%3, %4}; mov.b128 w, {u, v}; st.relaxed.gpu.global.b128 [%0], w; }"
               ::"l"(p), "r"(a), "r"(b), "r"(c), "r"(d) : "memory");
}
__device__ __forceinline__ uint4 ld_b128(const uint32_t* p) {
  uint4 r;
  asm volatile("{ .reg .b64 u, v; .reg .b128 w; ld.relaxed.gpu.global.b128 w, [%4]; mov.b128 {u, v}, w; mov.b64 {%0, %1}, u; mov.b64 {%2, %3}, v; }"
               : "=r"(r.x), "=r"(r.y), "=r"(r.z), "=r"(r.w) : "l"(p) : "memory");
  return r;
}
__device__ __forceinline__ void st_pairs(uint32_t* p, uint32_t a, uint32_t b, uint32_t tag) {
  asm volatile("{ .reg .b64 u, v; mov.b64 u, {%1, %3}; mov.b64 v, {%2, %3}; st.relaxed.gpu.global.v2.b64 [%0], {u, v}; }"
               ::"l"(p), "r"(a), "r"(b), "r"(tag) : "memory");
}
__device__ __forceinline__ uint4 ld_pairs(const uint32_t* p) {
  uint4 v;
  asm volatile("{ .reg .b64 u, v; ld.relaxed.gpu.global.v2.b64 {u, v}, [%4]; mov.b64 {%0, %1}, u; mov.b64 {%2, %3}, v; }"
               : "=r"(v.x), "=r"(v.y), "=r"(v.z), "=r"(v.w) : "l"(p) : "memory");
  return v;
}
__device__ __forceinline__ uint2 ld_pair(const uint32_t* p) {
  uint2 v;
  asm volatile("{ .reg .b64 u; ld.relaxed.gpu.global.b64 u, [%2]; mov.b64 {%0, %1}, u; }" : "=r"(v.x), "=r"(v.y) : "l"(p) : "memory");
  return v;
}
__device__ __forceinline__ void red_release(uint32_t* p, uint32_t v) {
  asm volatile("red.release.gpu.global.add.u32 [%0], %1;" ::"l"(p), "r"(v) : "memory");
}
__device__ __forceinline__ uint32_t ldg_nc1(const void* p) {
  uint32_t v;
  asm volatile("ld.global.nc.u32 %0, [%1];" : "=r"(v) : "l"(p));
  return v;
}
__device__ __forceinline__ uint4 ldg_nc4(const void* p) {
  uint4 v; asm volatile("ld.global.nc.L1::no_allocate.v4.u32 {%0,%1,%2,%3}, [%4];" : "=r"(v.x), "=r"(v.y), "=r"(v.z), "=r"(v.w) : "l"(p)); return v;
}
__device__ __forceinline__ uint4 ldg_stream4(const void* p) {
  uint4 v;
  asm volatile("ld.global.nc.L1::no_allocate.L2::cache_hint.v4.u32 {%0,%1,%2,%3}, [%4], %5;" : "=r"(v.x), "=r"(v.y), "=r"(v.z), "=r"(v.w) : "l"(p), "l"(l2_stream()));
  return v;
}
__device__ __forceinline__ void stg4(void* p, uint4 v) {
  asm volatile("st.global.v4.u32 [%0], {%1,%2,%3,%4};" ::"l"(p), "r"(v.x), "r"(v.y), "r"(v.z), "r"(v.w) : "memory");
}
__device__ __forceinline__ void wait_counter(const uint32_t* p, uint32_t target) {
  uint32_t n = 0;
  while ((int)(ld_acquire(p) - target) < 0) { watchdog(n); }
}
__device__ __forceinline__ uint32_t tagf(float v, uint32_t tag) { return (__float_as_uint(v) & ~3u) | tag; }
__device__ __forceinline__ bool tag_ok(uint4 v, uint32_t tag) { return (((v.x ^ tag) | (v.y ^ tag) | (v.z ^ tag) | (v.w ^ tag)) & 3u) == 0; }
__device__ __forceinline__ float untag_sum(uint32_t a, uint32_t b) { return __uint_as_float(a & ~3u) + __uint_as_float(b & ~3u); }
__device__ __forceinline__ uint4 poll4(const uint32_t* p, uint32_t tag) {
  uint4 v = ld_relaxed4(p);
  uint32_t n = 0;
  while (!tag_ok(v, tag)) { v = ld_relaxed4(p); watchdog(n); }
  return v;
}
__device__ __forceinline__ float bf_lo(uint32_t v) { return __uint_as_float(v << 16); }
__device__ __forceinline__ float bf_hi(uint32_t v) { return __uint_as_float(v & 0xffff0000u); }
__device__ __forceinline__ uint32_t pack_bf(float lo, float hi) {
  uint32_t r; asm("cvt.rn.bf16x2.f32 %0, %1, %2;" : "=r"(r) : "f"(hi), "f"(lo)); return r;
}
__device__ __forceinline__ float rbf(float v) { return __uint_as_float(pack_bf(0.f, v) & 0xffff0000u); }
__device__ __forceinline__ uint32_t hmul2(uint32_t a, uint32_t b) {
  uint32_t r; asm("mul.rn.bf16x2 %0, %1, %2;" : "=r"(r) : "r"(a), "r"(b)); return r;
}
__device__ __forceinline__ uint32_t hadd2(uint32_t a, uint32_t b) {
  uint32_t r; asm("add.rn.bf16x2 %0, %1, %2;" : "=r"(r) : "r"(a), "r"(b)); return r;
}
__device__ __forceinline__ uint32_t hsub2(uint32_t a, uint32_t b) {
  uint32_t r; asm("sub.rn.bf16x2 %0, %1, %2;" : "=r"(r) : "r"(a), "r"(b)); return r;
}
__device__ __forceinline__ uint32_t hmax2(uint32_t a, uint32_t b) {
  uint32_t r; asm("max.bf16x2 %0, %1, %2;" : "=r"(r) : "r"(a), "r"(b)); return r;
}
__device__ __forceinline__ float rcp(float x) { float r; asm("rcp.approx.ftz.f32 %0, %1;" : "=f"(r) : "f"(x)); return r; }
__device__ __forceinline__ float ex2(float x) { float r; asm("ex2.approx.ftz.f32 %0, %1;" : "=f"(r) : "f"(x)); return r; }
__device__ __forceinline__ void stmatrix4(uint32_t addr, uint32_t a, uint32_t b, uint32_t c, uint32_t d) {
  asm volatile("stmatrix.sync.aligned.m8n8.x4.shared.b16 [%0], {%1,%2,%3,%4};" ::"r"(addr), "r"(a), "r"(b), "r"(c), "r"(d) : "memory");
}
__device__ __forceinline__ void ldmatrix4(uint32_t addr, uint32_t& a, uint32_t& b, uint32_t& c, uint32_t& d) {
  asm volatile("ldmatrix.sync.aligned.m8n8.x4.shared.b16 {%0,%1,%2,%3}, [%4];" : "=r"(a), "=r"(b), "=r"(c), "=r"(d) : "r"(addr) : "memory");
}
__device__ __forceinline__ void ldmatrix4t(uint32_t addr, uint32_t& a, uint32_t& b, uint32_t& c, uint32_t& d) {
  asm volatile("ldmatrix.sync.aligned.m8n8.x4.trans.shared.b16 {%0,%1,%2,%3}, [%4];" : "=r"(a), "=r"(b), "=r"(c), "=r"(d) : "r"(addr) : "memory");
}
__device__ __forceinline__ void mma16816(float (&d)[4], uint32_t a0, uint32_t a1, uint32_t a2, uint32_t a3, uint32_t b0, uint32_t b1) {
  asm volatile("mma.sync.aligned.m16n8k16.row.col.f32.bf16.bf16.f32 {%0,%1,%2,%3}, {%4,%5,%6,%7}, {%8,%9}, {%0,%1,%2,%3};"
               : "+f"(d[0]), "+f"(d[1]), "+f"(d[2]), "+f"(d[3]) : "r"(a0), "r"(a1), "r"(a2), "r"(a3), "r"(b0), "r"(b1));
}
__device__ __forceinline__ void sts1(uint32_t a, uint32_t v) { asm volatile("st.shared.u32 [%0], %1;" ::"r"(a), "r"(v) : "memory"); }
__device__ __forceinline__ uint4 lds4(uint32_t a) {
  uint4 v; asm volatile("ld.shared.v4.u32 {%0,%1,%2,%3}, [%4];" : "=r"(v.x), "=r"(v.y), "=r"(v.z), "=r"(v.w) : "r"(a) : "memory"); return v;
}
__device__ __forceinline__ uint2 lds2(uint32_t a) {
  uint2 v; asm volatile("ld.shared.v2.u32 {%0,%1}, [%2];" : "=r"(v.x), "=r"(v.y) : "r"(a) : "memory"); return v;
}
__device__ __forceinline__ uint32_t lds1(uint32_t a) {
  uint32_t v; asm volatile("ld.shared.u32 %0, [%1];" : "=r"(v) : "r"(a) : "memory"); return v;
}
__device__ __forceinline__ void sts2(uint32_t a, uint32_t x, uint32_t y) { asm volatile("st.shared.v2.u32 [%0], {%1,%2};" ::"r"(a), "r"(x), "r"(y) : "memory"); }
__device__ __forceinline__ void sts4(uint32_t a, uint4 v) {
  asm volatile("st.shared.v4.u32 [%0], {%1,%2,%3,%4};" ::"r"(a), "r"(v.x), "r"(v.y), "r"(v.z), "r"(v.w) : "memory");
}
__device__ __forceinline__ float silu_f(float v) { return __fdividef(v, 1.f + __expf(-v)); }
__device__ __forceinline__ uint32_t hfma2(uint32_t a, uint32_t b, uint32_t c) {
  uint32_t r; asm("fma.rn.bf16x2 %0, %1, %2, %3;" : "=r"(r) : "r"(a), "r"(b), "r"(c)); return r;
}
__device__ __forceinline__ void split_inv(float sd, uint32_t& ih, uint32_t& il) {
  const float inv = rcp(sd);
  ih = pack_bf(inv, inv);
  const float lo = inv - bf_lo(ih);
  il = pack_bf(lo, lo);
}
__device__ __forceinline__ uint32_t ln_mod(uint32_t x, uint32_t mean2, uint32_t ih, uint32_t il, uint32_t c1, uint32_t sh) {
  const uint32_t d = hsub2(x, mean2);
  return hadd2(hmul2(hfma2(d, ih, hmul2(d, il)), c1), sh);
}

#define R8(a, i) "+f"(a[i]), "+f"(a[i + 1]), "+f"(a[i + 2]), "+f"(a[i + 3]), "+f"(a[i + 4]), "+f"(a[i + 5]), "+f"(a[i + 6]), "+f"(a[i + 7])
#define D64 "{%0,%1,%2,%3,%4,%5,%6,%7,%8,%9,%10,%11,%12,%13,%14,%15,%16,%17,%18,%19,%20,%21,%22,%23,%24,%25,%26,%27,%28,%29,%30,%31," \
            "%32,%33,%34,%35,%36,%37,%38,%39,%40,%41,%42,%43,%44,%45,%46,%47,%48,%49,%50,%51,%52,%53,%54,%55,%56,%57,%58,%59,%60,%61,%62,%63}"
template <int TB>
__device__ __forceinline__ void mma_ss(float (&d)[64], uint64_t da, uint64_t db, int sc) {
  asm volatile("{\n.reg .pred p;\nsetp.ne.b32 p, %66, 0;\n"
               "wgmma.mma_async.sync.aligned.m64n128k16.f32.bf16.bf16 " D64 ", %64, %65, p, 1, 1, 0, %67;\n}"
               : R8(d, 0), R8(d, 8), R8(d, 16), R8(d, 24), R8(d, 32), R8(d, 40), R8(d, 48), R8(d, 56)
               : "l"(da), "l"(db), "r"(sc), "n"(TB));
}
template <int TB>
__device__ __forceinline__ void mma_rs(float (&d)[64], uint32_t a0, uint32_t a1, uint32_t a2, uint32_t a3, uint64_t db, int sc) {
  asm volatile("{\n.reg .pred p;\nsetp.ne.b32 p, %69, 0;\n"
               "wgmma.mma_async.sync.aligned.m64n128k16.f32.bf16.bf16 " D64 ", {%64,%65,%66,%67}, %68, p, 1, 1, %70;\n}"
               : R8(d, 0), R8(d, 8), R8(d, 16), R8(d, 24), R8(d, 32), R8(d, 40), R8(d, 48), R8(d, 56)
               : "r"(a0), "r"(a1), "r"(a2), "r"(a3), "l"(db), "r"(sc), "n"(TB));
}
#define D128 "{%0,%1,%2,%3,%4,%5,%6,%7,%8,%9,%10,%11,%12,%13,%14,%15,%16,%17,%18,%19,%20,%21,%22,%23,%24,%25,%26,%27,%28,%29,%30,%31," \
             "%32,%33,%34,%35,%36,%37,%38,%39,%40,%41,%42,%43,%44,%45,%46,%47,%48,%49,%50,%51,%52,%53,%54,%55,%56,%57,%58,%59,%60,%61,%62,%63," \
             "%64,%65,%66,%67,%68,%69,%70,%71,%72,%73,%74,%75,%76,%77,%78,%79,%80,%81,%82,%83,%84,%85,%86,%87,%88,%89,%90,%91,%92,%93,%94,%95," \
             "%96,%97,%98,%99,%100,%101,%102,%103,%104,%105,%106,%107,%108,%109,%110,%111,%112,%113,%114,%115,%116,%117,%118,%119,%120,%121,%122,%123,%124,%125,%126,%127}"
#define R128(d, e) R8(d, 0), R8(d, 8), R8(d, 16), R8(d, 24), R8(d, 32), R8(d, 40), R8(d, 48), R8(d, 56), \
                   R8(e, 0), R8(e, 8), R8(e, 16), R8(e, 24), R8(e, 32), R8(e, 40), R8(e, 48), R8(e, 56)
__device__ __forceinline__ void mma256_ss(float (&d)[64], float (&e)[64], uint64_t da, uint64_t db, int sc) {
  asm volatile("{\n.reg .pred p;\nsetp.ne.b32 p, %130, 0;\n"
               "wgmma.mma_async.sync.aligned.m64n256k16.f32.bf16.bf16 " D128 ", %128, %129, p, 1, 1, 0, 1;\n}"
               : R128(d, e) : "l"(da), "l"(db), "r"(sc));
}
__device__ __forceinline__ void mma256_rs(float (&d)[64], float (&e)[64], uint32_t a0, uint32_t a1, uint32_t a2, uint32_t a3, uint64_t db) {
  asm volatile("{\n.reg .pred p;\nsetp.ne.b32 p, 1, 0;\n"
               "wgmma.mma_async.sync.aligned.m64n256k16.f32.bf16.bf16 " D128 ", {%128,%129,%130,%131}, %132, p, 1, 1, 1;\n}"
               : R128(d, e) : "r"(a0), "r"(a1), "r"(a2), "r"(a3), "l"(db));
}
template <int N> __device__ __forceinline__ void keep(float (&a)[N]) {
#pragma unroll
  for (int i = 0; i < N; i++) asm volatile("" : "+f"(a[i])::"memory");
}
template <int N> __device__ __forceinline__ void keep(uint32_t (&a)[N]) {
#pragma unroll
  for (int i = 0; i < N; i++) asm volatile("" : "+r"(a[i])::"memory");
}

#define STAMP(idx) do {} while (0)
#define PROF(grp, cond, idx) do {} while (0)

constexpr float SCL2 = 1.4426950408889634f * 0.08838834764831845f;

__device__ __forceinline__ void pack_p(const float (&s)[64], uint32_t (&p)[32]) {
#pragma unroll
  for (int i = 0; i < 32; i++) p[i] = pack_bf(s[2 * i], s[2 * i + 1]);
}

__device__ __forceinline__ void issue_qk(float (&s)[64], uint32_t q0, uint32_t q1, uint32_t kslot) {
  const uint64_t db = make_desc(kslot, 16, 1024), da0 = make_desc(q0, 16, 1024), da1 = make_desc(q1, 16, 1024);
#pragma unroll
  for (int kk = 0; kk < 8; kk++) mma_ss<0>(s, (kk < 4 ? da0 : da1) + (kk & 3) * 2, db + (kk >> 2) * 1024 + (kk & 3) * 2, kk != 0);
}
__device__ __forceinline__ void issue_pv(float (&o)[64], uint32_t (&p)[32], uint32_t vslot, int acc) {
  uint64_t db = make_desc(vslot, 16384, 1024);
#pragma unroll
  for (int kk = 0; kk < 8; kk++)
    mma_rs<1>(o, p[4 * kk], p[4 * kk + 1], p[4 * kk + 2], p[4 * kk + 3], db + kk * 128, kk == 0 ? acc : 1);
}

template <int H>
__device__ __forceinline__ void store_chunk(const float (&a)[64], uint32_t addr) {
#pragma unroll
  for (int i = 8 * H; i < 8 * H + 8; i += 2)
    stmatrix4(addr ^ ((i & 7) << 4), pack_bf(a[4 * i], a[4 * i + 1]), pack_bf(a[4 * i + 2], a[4 * i + 3]),
              pack_bf(a[4 * i + 4], a[4 * i + 5]), pack_bf(a[4 * i + 6], a[4 * i + 7]));
}
template <int H>
__device__ __forceinline__ void store_chunk(const float (&a)[64], float i0, float i1, uint32_t addr) {
#pragma unroll
  for (int i = 8 * H; i < 8 * H + 8; i += 2)
    stmatrix4(addr ^ ((i & 7) << 4), pack_bf(a[4 * i] * i0, a[4 * i + 1] * i0), pack_bf(a[4 * i + 2] * i1, a[4 * i + 3] * i1),
              pack_bf(a[4 * i + 4] * i0, a[4 * i + 5] * i0), pack_bf(a[4 * i + 6] * i1, a[4 * i + 7] * i1));
}
__device__ __forceinline__ float inv_quad_sum(float l) {
  l += __shfl_xor_sync(0xffffffffu, l, 1);
  l += __shfl_xor_sync(0xffffffffu, l, 2);
  return rcp(l);
}

__device__ __forceinline__ void ln_scalars(float mean, float var, float& mb, float& sd) {
  mb = rbf(mean);
  float r; asm("sqrt.approx.ftz.f32 %0, %1;" : "=f"(r) : "f"(rbf(rbf(var) + 1e-5f)));
  sd = rbf(r);
}

__global__ void __cluster_dims__(2, 1, 1) __launch_bounds__(384, 1) fused_kernel(const __grid_constant__ Maps maps, const Ptrs P) {
  extern __shared__ __align__(1024) uint8_t smem_raw[];
  const uint32_t base = smem_u32(smem_raw);
  const int tid = threadIdx.x, lane = tid & 31;
  const int warp = __shfl_sync(0xffffffffu, tid >> 5, 0);
  const int b = blockIdx.x;
  PROF(31, tid == 0, 0);

  if (b >= NMAIN) {
    float* sc = reinterpret_cast<float*>(smem_raw);
    float* red = sc + DM;
    for (int k = tid; k < DM; k += 384) sc[k] = rbf(silu_f(__bfloat162float(P.c[k])));
    __syncthreads();
    if (tid < 256) {
      const int col = 2048 + (b - NMAIN) * 1024 + (tid & 127) * 8, r0 = (tid >> 7) * 512;
      float acc[8];
#pragma unroll
      for (int e = 0; e < 8; e++) acc[e] = 0.f;
#pragma unroll 1
      for (int r = r0; r < r0 + 512; r += HU) {
        uint4 w[HU];
#pragma unroll
        for (int u = 0; u < HU; u++) w[u] = ldg_stream4(P.w_mod + (size_t)(r + u) * NMOD + col);
#pragma unroll
        for (int u = 0; u < HU; u++) {
          float s = sc[r + u];
          acc[0] += s * bf_lo(w[u].x); acc[1] += s * bf_hi(w[u].x); acc[2] += s * bf_lo(w[u].y); acc[3] += s * bf_hi(w[u].y);
          acc[4] += s * bf_lo(w[u].z); acc[5] += s * bf_hi(w[u].z); acc[6] += s * bf_lo(w[u].w); acc[7] += s * bf_hi(w[u].w);
        }
      }
      if (tid >= 128) {
#pragma unroll
        for (int e = 0; e < 8; e++) red[(tid & 127) * 8 + e] = acc[e];
      }
      const uint32_t tag = ld_relaxed(&g_epoch) % 3 + 1;
      bar_sync(1, 256);
      if (tid < 128) {
        uint32_t o[8];
#pragma unroll
        for (int e = 0; e < 8; e++) o[e] = __float_as_uint(rbf(acc[e] + red[tid * 8 + e])) | tag;
        st_relaxed4(g_mod + col, o[0], o[1], o[2], o[3]);
        st_relaxed4(g_mod + col + 4, o[4], o[5], o[6], o[7]);
        const uint4 wr = ldg_nc4(P.w_r + tid * 8);
        const uint32_t wv[4] = {wr.x, wr.y, wr.z, wr.w};
        float dsum = 0.f;
#pragma unroll
        for (int e = 0; e < 8; e++) {
          const float m = bf_hi(o[e]);
          dsum += (b == NMAIN + 2 ? rbf(1.f + m) : m) * ((e & 1) ? bf_hi(wv[e >> 1]) : bf_lo(wv[e >> 1]));
        }
#pragma unroll
        for (int k = 16; k > 0; k >>= 1) dsum += __shfl_xor_sync(0xffffffffu, dsum, k);
        if (lane == 0) st_relaxed(g_mod + (b - NMAIN) * 4 + warp, tagf(dsum, tag));
      }
    }
    PROF(2, tid == 0, 1);
    return;
  }

  const int rank = b & 1;
  const int rb = ((b >> 4) << 1) | rank, cj = (b >> 1) & 7;
  const uint32_t bfull = base + OFF_BAR, bempty = bfull + NSLOT * 8;
  const uint32_t gfull = bempty + NSLOT * 8, gempty = gfull + 32;
  const uint32_t bar_ofull = gempty + 32;
  const uint32_t bar_ofree = bar_ofull + 16;
  const uint32_t bar_par = bar_ofree + 32;
  const uint32_t bar_mod = bar_par + 8;
  const uint32_t bar_pread = bar_mod + 8;
  const uint32_t bar_xres = bar_pread + 8;
  const uint32_t bar_ring = bar_xres + 8;
  const uint32_t bar_box = bar_ring + 24;
  const uint32_t bar_go = bar_box + 96;
  const uint32_t bar_go2 = bar_go + 16;
  const uint32_t bar_cnt = bar_go + 24;
  const uint32_t xfull = bar_go + 32, xempty = xfull + 32;
  const uint32_t bar_hw = xempty + 32, bar_hx = bar_hw + 8;
  const uint32_t bar_hpub = bar_hx + 16;
  const uint32_t bar_win = bar_hpub + 8;
  const uint32_t bar_rx = bar_win + 8;
  const uint32_t bar_sel = bar_rx + 8;
  const uint32_t bar_gate = bar_sel + 8;
  const uint32_t bar_res = bar_go + 8;
  const uint32_t stage = base + OFF_STAGE, par = base + OFF_PAR;

  if (warp == 8 && elect_one()) {
    for (int s = 0; s < NSLOT; s++) { mbar_init(bfull + s * 8, 1); mbar_init(bempty + s * 8, 16); }
    for (int s = 0; s < 4; s++) { mbar_init(gfull + s * 8, 1); mbar_init(gempty + s * 8, 16); mbar_init(xfull + s * 8, 1); mbar_init(xempty + s * 8, 8); mbar_init(bar_ofree + s * 8, 1); }
    mbar_init(bar_ofull, 128); mbar_init(bar_ofull + 8, 128);
    mbar_init(bar_par, 64); mbar_init(bar_mod, 256); mbar_init(bar_pread, 8); mbar_init(bar_xres, 1);
    mbar_init(bar_ring, 8); mbar_init(bar_ring + 8, 8); mbar_init(bar_ring + 16, 8);
    mbar_init(bar_go, 1); mbar_init(bar_go2, 1); mbar_init(bar_cnt, 1); mbar_init(bar_hpub, 8); mbar_init(bar_res, 1); mbar_init(bar_win, 1); mbar_init(bar_rx, 1); mbar_init(bar_sel, 64); mbar_init(bar_gate, 8);
    for (int s = 0; s < 12; s++) mbar_init(bar_box + s * 8, 1);
    asm volatile("fence.mbarrier_init.release.cluster;" ::: "memory");
    prefetch_map(&maps.x); prefetch_map(&maps.wq); prefetch_map(&maps.k); prefetch_map(&maps.v);
  }
  if (warp == 9 && elect_one()) {
    mbar_init(bar_hw, 1); mbar_init(bar_hx, 1); mbar_init(bar_hx + 8, 1);
    asm volatile("fence.mbarrier_init.release.cluster;" ::: "memory");
    mbar_expect_tx(bar_hw, 32768);
    mbar_expect_tx(bar_hx, 16384);
    mbar_expect_tx(bar_hx + 8, 16384);
    const __nv_bfloat16* xs = P.x + (size_t)(rb * 128 + cj * 16) * DM;
    bulk_load(base + 2 * GST_BYTES, xs, 16384, bar_hx);
    tma2d(stage, &maps.wm, (b >> 1) * 32, rank * 512, bar_hw);
    tma2d(stage + 16384, &maps.wm, (b >> 1) * 32, rank * 512 + 256, bar_hw);
    bulk_load(base + 3 * GST_BYTES, xs + 8 * DM, 16384, bar_hx + 8);
  }
  cluster_arrive();

  if (warp >= 8) {
    asm volatile("setmaxnreg.dec.sync.aligned.u32 40;");
    if (warp < 10) bar_arrive(1, 320);
    const uint32_t epoch = ld_relaxed(&g_epoch);
    cluster_wait();
    if (warp == 8) {
      const int kvrow = (cj >> 1) * SK + (SK - WIN);
      int wch = cj * 8 + rank * 2;
#pragma unroll 1
      for (int ps = 0; ps < 3; ps++) {
        const CUtensorMap* mw = ps == 2 ? &maps.wo : &maps.wq;
        const uint32_t xt = ps == 1 ? XT1 : XT2, wt = ps == 0 ? WT0 : (ps == 1 ? WT1 : WT2);
        const int nst = ps == 2 ? 32 : 16;
        if (ps) {
          mbar_wait(bar_ofree + (ps - 1) * 16, 0);
          fence_async();
        }
#pragma unroll 1
        for (int i = 0; i < nst; i++) {
          const uint32_t bf = gfull + (i & 3) * 8;
          const int kt = ps == 2 ? (((cj & 1) * 4 + ((i >> 1) & 3)) * 4 + (i >> 3)) * 2 + (i & 1) : (i + (ps ? 0 : b & 14)) & 15;
          const uint32_t wd = base + unit_of(wt, i & 3) + rank * UNIT, xd = base + unit_of(xt, i & 3);
          const uint8_t* xs = g_act + (uint32_t)(rb * 80 + (ps - 1) * 16 + kt) * UNIT;
          if (ps == 0 && i == HD) mbar_wait(bar_mod, 0);
          if (ps && i && i < 4) mbar_wait(bempty + (i == 3 ? 3 : i - 1) * 8, 1);
          mbar_wait(gempty + (i & 3) * 8, ((i >> 2) & 1) ^ 1);
          if (elect_one()) {
            mbar_expect_tx(bf, ps ? GST_BYTES : 2 * UNIT);
            tma3d_mc<true>(wd, mw, 0, (i == 31 ? kt ^ (rank * 32) : kt) * 64, i == 31 ? cj * 2 : wch, bf);
          }
          if (ps) {
            if (i == 16) mbar_wait(bar_cnt, 0);
            if (i == 2) mbar_wait(bempty + 16, 1);
            if (elect_one()) {
              if (i == 31) bulk_load(xd, xs, UNIT, bf); else bulk_load_stream(xd, xs, UNIT, bf);
              mbar_arrive_pred(bar_go, i == GOST - 1);
              mbar_arrive_pred(bar_go2, ps * 16 + i == PG0);
              mbar_arrive_pred(bar_res, ((1u << RES0 | 1u << RES1) >> i) & 1);
              if (ps == 2 && b < NFFN && i >= PD0 && i < PD0 + 16)
                asm volatile("cp.async.bulk.prefetch.L2.global [%0], 4096;" ::"l"(P.w_down + (size_t)b * 32768 + (i - PD0) * 2048) : "memory");
            }
          }
        }
        if (ps == 2) break;
        wch = ps ? ((wch >> 3) ^ rank) * 2 : wch + 4;
#pragma unroll 1
        for (int u = 0; u < 16; u++) {
          const bool isk = (u == 0) || ((u & 1) && u < 15);
          const int blk = (isk ? (u + 1) >> 1 : (u == 15 ? 7 : (u >> 1) - 1)) & 3;
          const uint32_t sl = base + unit_of(ps ? AT1 : AT0, u & 3) + rank * UNIT, bf = bfull + (u & 3) * 8;
          if (u < 4) mbar_wait(gempty + ((u + 1) >> 1) * 8, 1);
          mbar_wait(bempty + (u & 3) * 8, ((u >> 2) & 1) ^ 1);
          if (elect_one()) {
            mbar_expect_tx(bf, SLOT_BYTES);
            tma3d_mc<false>(sl, isk ? &maps.k : &maps.v, 0, kvrow + blk * 128, rank, bf);
            if (ps && u >= PF2T && u < PF2T + 2 * PF2 && !((u - PF2T) & 1))
              tma3d_prefetch(&maps.wo, 0, ((((cj & 1) * 4 + (b >> 5)) * 4 + ((u - PF2T) >> 1)) * 2 + ((b >> 4) & 1)) * 64, (cj ^ rank) * 2);
          }
        }
      }
      mbar_wait(bar_ring, 0);
      if (elect_one()) {
        mbar_expect_tx(bar_rx, UNIT);
        bulk_load_stream(base + 8 * UNIT, g_act + (uint32_t)(rb * 80 + 16 + 63 - (cj & 1) * 32) * UNIT, UNIT, bar_rx);
      }
      if (b < NFFN) {
#pragma unroll 1
        for (int u = 0; u < 12; u++) {
          if (u == 2 || u == 8) mbar_wait(bar_ring + 8 + (u & 8), 0);
          if (u >= FPACE) mbar_wait(bar_box + (u - FPACE) * 8, 0);
          const uint32_t dst = base + unit_of(u < 4 ? FT_G : (u < 8 ? FT_U : FT_D), u & 3);
          if (elect_one()) {
            mbar_expect_tx(bar_box + u * 8, UNIT);
            if (u < 8) tma2d(dst, u < 4 ? &maps.wg : &maps.wu, b * 32, (u & 3) * 256, bar_box + u * 8);
            else tma3d(dst, &maps.wd, 0, b * 32, (u - 8) * 4, bar_box + u * 8);
          }
        }
      }
    } else if (warp == 9) {
      const uint32_t target = 8 * (epoch + 1);
#pragma unroll 1
      for (int i = 0; i < 16; i++) {
        if (i == HDX) mbar_wait(bar_mod, 0);
        if (i == NRS) {
          wait_counter(&g_cnt_h[rb * 32], target);
          PROF(1, lane == 0, 26);
          fence_async();
        }
        mbar_wait(xempty + (i & 3) * 8, ((i >> 2) & 1) ^ 1);
        if (elect_one()) {
          mbar_expect_tx(xfull + (i & 3) * 8, UNIT);
          if (i < NRS) tma2d(base + (i & 3) * GST_BYTES, &maps.x, ((2 * cj + i) & 15) * 64, rb * 128, xfull + (i & 3) * 8);
          else bulk_load_stream(base + (i & 3) * GST_BYTES, g_act + (uint32_t)(rb * 80 + ((2 * cj + i) & 15)) * UNIT, UNIT, xfull + (i & 3) * 8);
        }
      }
      prefetch_map(&maps.wo);
#pragma unroll 1
      for (int t = 0; t < 4; t++) {
#pragma unroll 1
        for (int w = 0; w < 2; w++) {
          mbar_wait(bar_ofull + w * 8, t & 1);
          uint8_t* dst = g_act + (uint32_t)(rb * 80 + 16 + (cj * 4 + t) * 2) * UNIT + w * 8192;
          if (elect_one()) {
            bulk_store(dst, base + unit_of(QT, 2 * t) + w * 8192, 8192);
            bulk_store(dst + UNIT, base + unit_of(QT, 2 * t + 1) + w * 8192, 8192);
            asm volatile("cp.async.bulk.commit_group;" ::: "memory");
          }
        }
        if (elect_one()) {
          asm volatile("cp.async.bulk.wait_group.read 0;" ::: "memory");
          mbar_arrive(bar_ofree + t * 8);
          asm volatile("cp.async.bulk.wait_group 0;" ::: "memory");
          fence_async();
          red_release(&g_cnt_o[((rb * 4 + t) * 2 + (cj >> 2)) * 32], 2);
        }
        if (t & 1) {
          wait_counter(&g_cnt_o[(rb * 8 + 2 * t - 2 + (cj & 1)) * 32], target);
          wait_counter(&g_cnt_o[(rb * 8 + 2 * t + (cj & 1)) * 32], target);
        }
      }
      wait_counter(&g_cnt_o[(rb * 8 + 7 - (cj & 1)) * 32], target);
      fence_async();
      if (elect_one()) {
        mbar_arrive(bar_cnt);
        PROF(2, true, 27);
        mbar_expect_tx(bar_xres, 32768);
      }
#pragma unroll 1
      for (int u = 0; u < 2; u++) {
        mbar_wait(bar_res, u);
        if (elect_one()) tma2d(base + OFF_RES + u * UNIT, &maps.x, cj * 128 + u * 64, rb * 128, bar_xres);
      }
      const uint32_t tag = epoch % 3 + 1;
      const uint32_t* inbox = g_cand + (lane & 15);
      mbar_wait(bar_ring + 16, 0);
      uint32_t c0 = ld_relaxed(inbox), n = 0;
#define CAND_STEP(cv)                                                                                        \
      {                                                                                                      \
        const bool valid = (cv & 3u) == tag, all = __all_sync(0xffffffffu, valid);                           \
        const uint32_t best = __reduce_max_sync(0xffffffffu, valid ? cv : 0u);                               \
        const uint32_t blk = __ffs(__ballot_sync(0xffffffffu, cv == best)) - 1;                              \
        if (best) sts2(par + PAR_CONST + 56, best, (blk << 7 | (~best >> 2 & 127)) | (all ? 0x1800 : 0x800)); \
        if (all) break;                                                                                      \
        cv = ld_relaxed(inbox);                                                                              \
      }
      while (true) { CAND_STEP(c0) watchdog(n); }
    } else {
      const int t2 = tid - 320;
      if (t2 == 0) {
        mbar_wait(bar_hpub, 0);
        PROF(1, true, 24);
        red_release(&g_cnt_h[rb * 32], 1);
        PROF(1, true, 25);
        prefetch_map(&maps.wg); prefetch_map(&maps.wu); prefetch_map(&maps.wd); prefetch_map(&maps.out);
      }
      __syncwarp();
      if (b < NFFN) {
        mbar_wait(bar_go2, 0);
        const __nv_bfloat16* pg = ((b & 1) ? P.w_up : P.w_gate) + (b >> 1) * 64 + (size_t)t2 * FF;
        const __nv_bfloat16* pd = P.w_down + (size_t)b * 32768 + t2 * 64;
        PROF(2, t2 == 0, 13);
#pragma unroll 1
        for (int i = 0; i < WN; i += WB) {
          uint32_t v[WB];
#pragma unroll
          for (int u = 0; u < WB; u++)
            asm volatile("ld.global.cg.L2::128B.u32 %0, [%1];" : "=r"(v[u]) : "l"(i < 16 ? pg + (size_t)(i + u) * 64 * FF : pd + (i + u - 16) * 4096));
#pragma unroll
          for (int u = 1; u < WB; u++) v[0] ^= v[u];
          sts1(par + PAR_SINK + t2 * 4, v[0]);
        }
        PROF(2, t2 == 0, 14);
      }
      const uint32_t tag = epoch % 3 + 1;
      mbar_wait(bar_go, 0);
      if (warp == 10) {
        const uint32_t* src = g_mod + 2 * DM + cj * 128 + lane * 4;
        const uint2 wr = *reinterpret_cast<const uint2*>(P.w_r + cj * 128 + lane * 4);
        uint4 vga, vsb, vcb, vgb;
        uint32_t n = 0;
        do {
          vga = ld_relaxed4(src); vsb = ld_relaxed4(src + DM); vcb = ld_relaxed4(src + 2 * DM); vgb = ld_relaxed4(src + 3 * DM);
          watchdog(n);
        } while (!(tag_ok(vga, tag) && tag_ok(vsb, tag) && tag_ok(vcb, tag) && tag_ok(vgb, tag)));
        const float c0 = rbf(1.f + bf_hi(vcb.x)), c1 = rbf(1.f + bf_hi(vcb.y)), c2 = rbf(1.f + bf_hi(vcb.z)), c3 = rbf(1.f + bf_hi(vcb.w));
        const float a0 = c0 * bf_lo(wr.x), a1 = c1 * bf_hi(wr.x), a2 = c2 * bf_lo(wr.y), a3 = c3 * bf_hi(wr.y);
        const uint32_t h0 = pack_bf(a0, a1), h1 = pack_bf(a2, a3);
        const uint32_t t1 = par + PAR_T1 + (lane >> 2) * 64 + (lane & 1) * 32 + (lane & 2) * 2;
        sts1(t1, h0); sts1(t1 + 8, pack_bf(a0 - bf_lo(h0), a1 - bf_hi(h0)));
        sts1(t1 + 16, h1); sts1(t1 + 24, pack_bf(a2 - bf_lo(h1), a3 - bf_hi(h1)));
        sts4(par + PAR_T2 + lane * 32, make_uint4(pack_bf(c0, c1), __byte_perm(vsb.x, vsb.y, 0x7632), __byte_perm(vgb.x, vgb.y, 0x7632), __byte_perm(vga.x, vga.y, 0x7632)));
        sts4(par + PAR_T2 + lane * 32 + 16, make_uint4(pack_bf(c2, c3), __byte_perm(vsb.z, vsb.w, 0x7632), __byte_perm(vgb.z, vgb.w, 0x7632), __byte_perm(vga.z, vga.w, 0x7632)));
      } else if (lane < 4) {
        const uint4 g = poll4(lane < 2 ? g_mod + 5 * DM + b * 8 + lane * 4 : g_mod + 16 - lane * 4, tag);
        sts1(par + PAR_CONST + 60, 0);
        if (lane < 2) sts4(par + PAR_CONST + 16 + lane * 16, g);
        else sts2(par + PAR_CONST + (lane - 2) * 8, __float_as_uint(untag_sum(g.x, g.y) + untag_sum(g.z, g.w)), epoch);
      }
      __syncwarp();
#pragma unroll 4
      for (int q = XR; q < XE; q++) st_b128(g_xch + ((size_t)b * 8 * 256 + q * 64 + t2) * 4, (epoch & 1) << 16, 0, 0, 0);
      for (int q = 0; q < 2; q++) st_relaxed4(g_stats + ((size_t)cj * SEQ + rb * 128 + q * 64 + t2) * 4, 0, 0, 0, 0);
      if (b < NFFN)
        for (int q = 0; q < 4; q++) st_relaxed4(g_ypart + ((size_t)(q * 32 + (t2 >> 1)) * NFFN + b) * 8 + (t2 & 1) * 4, 0, 0, 0, 0);
      st_relaxed4(g_row + rb * 2 * DM + (t2 >> 5) * DM + cj * 128 + (t2 & 31) * 4, 0, 0, 0, 0);
      __threadfence();
      mbar_arrive(bar_par);
      mbar_wait(bar_gate, 0);
      uint32_t have = 0, n = 0;
      while (true) {
        const uint32_t st = lds1(par + PAR_CONST + 60) >> 7;
        if ((st & 31) != have) {
          const uint32_t* hsrc = g_row + (st & 15) * 2 * DM + t2 * 4;
          uint4 hv[4];
          bool ok = true;
#pragma unroll
          for (int i = 0; i < 4; i++) hv[i] = ld_pairs(hsrc + i * 256);
#pragma unroll
          for (int i = 0; i < 4; i++) {
            sts2(base + ((FT_G >> i * 4) & 15) * UNIT + (warp & 1) * 8192 + 256 + lane * 8, hv[i].x, hv[i].z);
            ok = ok && hv[i].y == tag && hv[i].w == tag;
          }
          have = __all_sync(0xffffffffu, ok) ? st & 31 : 0;
        }
        if ((st ^ have) == 32) break;
        watchdog(n);
      }
      mbar_arrive(bar_sel);
    }
    __syncwarp();
    cluster_arrive();
    {
      const uint32_t tag = epoch % 3 + 1, t3 = tid - 256;
      mbar_wait(bar_win, 0);
      uint2 win = lds2(par + PAR_CONST + 56);
      win.y &= 0x7ff;
      const uint32_t* fsrc = g_row + (win.y >> 7) * 2 * DM + (b >> 1) * 16 + (t3 & 3) * 4 + (b & 1) * 2;
      const uint32_t* ysrc = g_ypart + (size_t)b * NFFN * 8 + min(t3, NFFN - 1) * 4;
      uint2 fh = ld_pair(fsrc), fx = ld_pair(fsrc + DM);
      if (PSL) __nanosleep(PSL);
      uint4 ya = ld_relaxed4(ysrc), yb = ld_relaxed4(ysrc + NFFN * 4);
      const float rwin = __uint_as_float(((int)win.x < 0 ? win.x & 0x7fffffffu : ~win.x) & ~0x1ffu);
      const float rs = rbf(rcp(1.f + __expf(-rbf(rwin))));
      uint32_t n = 0;
      while (fh.y != tag || fx.y != tag) { fh = ld_pair(fsrc); fx = ld_pair(fsrc + DM); watchdog(n); }
      while (!(tag_ok(ya, tag) && tag_ok(yb, tag))) {
        if (!tag_ok(ya, tag)) ya = ld_relaxed4(ysrc);
        if (!tag_ok(yb, tag)) yb = ld_relaxed4(ysrc + NFFN * 4);
        watchdog(n);
      }
      __syncwarp();
      PROF(8, t3 == 0, 5);
      float y0 = untag_sum(ya.x, yb.x), y1 = untag_sum(ya.y, yb.y), y2 = untag_sum(ya.z, yb.z), y3 = untag_sum(ya.w, yb.w);
      const bool u1 = lane & 2, u2 = lane & 4;
      y0 = (u1 ? y2 : y0) + __shfl_xor_sync(0xffffffffu, u1 ? y0 : y2, 2);
      y1 = (u1 ? y3 : y1) + __shfl_xor_sync(0xffffffffu, u1 ? y1 : y3, 2);
      y0 = (u2 ? y1 : y0) + __shfl_xor_sync(0xffffffffu, u2 ? y0 : y1, 4);
      y0 += __shfl_xor_sync(0xffffffffu, y0, 8);
      if (!(lane & 8)) sts1(par + PAR_RED + 64 + (t3 >> 4) * 32 + ((lane & 1) * 4 + (lane & 2) + ((lane >> 2) & 1)) * 4, __float_as_uint(y0));
      bar_sync(4, 128);
      if (t3 < 4) {
        y0 = 0.f; y1 = 0.f;
#pragma unroll
        for (int w4 = 0; w4 < 7; w4++) {
          const uint2 v = lds2(par + PAR_RED + 64 + w4 * 32 + t3 * 8);
          y0 += __uint_as_float(v.x); y1 += __uint_as_float(v.y);
        }
        const uint2 gv = lds2(par + PAR_CONST + 16 + t3 * 8);
        const uint32_t upd = hmul2(pack_bf(y0, y1), pack_bf(rs, rs));
        *reinterpret_cast<uint32_t*>(P.out + (size_t)win.y * DM + b * 8 + t3 * 2) =
            hadd2(fx.x, hmul2(__byte_perm(gv.x, gv.y, 0x7632), hadd2(fh.x, upd)));
        if (b == 0 && t3 == 0) st_relaxed(&g_epoch, epoch + 1);
      }
      PROF(31, t3 == 0, 36);
    }
    cluster_wait();
  } else {
    const int wg = warp >> 2;

    uint32_t tag;
    {
      uint32_t* const pmod = g_modp + rank * 2 * DM + (b >> 1) * 32 + lane;
      uint32_t* const pln = g_ln1 + (rb * 128 + cj * 16 + warp) * 4;
      const uint32_t cv = ldg_nc1(P.c + rank * 512 + tid * 2);
      const uint32_t epoch = ld_relaxed(&g_epoch);
      if (warp == 0) st_relaxed(pmod, 0);
      if (lane == 0) { st_relaxed2(pln, 0, 0); st_relaxed2(pln + 32, 0, 0); }
      asm volatile("setmaxnreg.inc.sync.aligned.u32 232;");
      sts1(par + tid * 4, pack_bf(silu_f(bf_lo(cv)), silu_f(bf_hi(cv))));
      bar_sync(1, 320);
      tag = epoch % 3 + 1;
#pragma unroll
      for (int part = 0; part < 3; part++) {
        if (part != 1) {
          const uint32_t xa = base + (2 + part / 2) * GST_BYTES + warp * 2048 + lane * 16;
          mbar_wait(bar_hx + part * 4, 0);
          float s0 = 0.f, s1 = 0.f, q0 = 0.f, q1 = 0.f;
#pragma unroll
          for (int q = 0; q < 4; q++) {
            const uint4 xv = lds4(xa + q * 512);
            const uint32_t u[4] = {xv.x, xv.y, xv.z, xv.w};
#pragma unroll
            for (int e = 0; e < 4; e++) { const float lo = bf_lo(u[e]), hi = bf_hi(u[e]); s0 += lo; s1 += hi; q0 += lo * lo; q1 += hi * hi; }
          }
          s0 += s1; q0 += q1;
#pragma unroll
          for (int o = 16; o > 0; o >>= 1) { s0 += __shfl_xor_sync(0xffffffffu, s0, o); q0 += __shfl_xor_sync(0xffffffffu, q0, o); }
          const float mean = s0 * (1.f / DM);
          float mb, sd;
          ln_scalars(mean, fmaxf(q0 * (1.f / DM) - mean * mean, 0.f), mb, sd);
          if (lane == 0) st_relaxed2(pln + part * 16, __float_as_uint(mb) | tag, __float_as_uint(sd) | tag);
          PROF(1, tid == 0 && part == 2, 4);
        } else {
          float acc[8];
#pragma unroll
          for (int e = 0; e < 8; e++) acc[e] = 0.f;
          const uint32_t wa = stage + (tid >> 2) * 64 + (((tid ^ (tid >> 3)) & 3) << 4), sa = par + (tid >> 3) * 4, sh = (tid & 4) ? 0x3244 : 0x1044;
          mbar_wait(bar_hw, 0);
#pragma unroll
          for (int p = 0; p < 8; p++) {
            const uint4 w = lds4(wa + p * 4096);
            const float s = __uint_as_float(__byte_perm(lds1(sa + p * 128), 0, sh));
            acc[0] += s * bf_lo(w.x); acc[1] += s * bf_hi(w.x); acc[2] += s * bf_lo(w.y); acc[3] += s * bf_hi(w.y);
            acc[4] += s * bf_lo(w.z); acc[5] += s * bf_hi(w.z); acc[6] += s * bf_lo(w.w); acc[7] += s * bf_hi(w.w);
          }
#pragma unroll
          for (int e = 0; e < 4; e++) {
            const bool up = lane & 16;
            acc[e] = (up ? acc[e + 4] : acc[e]) + __shfl_xor_sync(0xffffffffu, up ? acc[e] : acc[e + 4], 16);
          }
#pragma unroll
          for (int e = 0; e < 2; e++) {
            const bool up = lane & 8;
            acc[e] = (up ? acc[e + 2] : acc[e]) + __shfl_xor_sync(0xffffffffu, up ? acc[e] : acc[e + 2], 8);
          }
          {
            const bool up = lane & 4;
            acc[0] = (up ? acc[1] : acc[0]) + __shfl_xor_sync(0xffffffffu, up ? acc[0] : acc[1], 4);
          }
          sts1(par + 1024 + warp * 128 + ((lane & 3) * 8 + (lane >> 2)) * 4, __float_as_uint(acc[0]));
          bar_sync(1, 256);
          if (warp == 0) {
            float s = 0.f;
#pragma unroll
            for (int w8 = 0; w8 < 8; w8++) s += __uint_as_float(lds1(par + 1024 + w8 * 128 + lane * 4));
            st_relaxed(pmod, (__float_as_uint(s) & ~3u) | tag);
          }
          PROF(1, tid == 0, 3);
        }
      }
      {
        uint2 s0 = ld_relaxed2(g_ln1 + (rb * 128 + (tid & 127)) * 4);
        uint4 v[4];
#pragma unroll
        for (int q = 0; q < 4; q++) v[q] = ld_relaxed4(g_modp + q * DM + tid * 4);
        {
          uint32_t n = 0;
          while (!(tag_ok(v[0], tag) && tag_ok(v[1], tag) && tag_ok(v[2], tag) && tag_ok(v[3], tag))) {
#pragma unroll
            for (int q = 0; q < 4; q++)
              if (!tag_ok(v[q], tag)) v[q] = ld_relaxed4(g_modp + q * DM + tid * 4);
            if (((s0.x ^ tag) | (s0.y ^ tag)) & 3u) s0 = ld_relaxed2(g_ln1 + (rb * 128 + (tid & 127)) * 4);
            watchdog(n);
          }
        }
        const uint32_t d = stage + (tid >> 2) * 64 + (tid & 1) * 32 + (tid & 2) * 2;
        sts1(d, pack_bf(1.f + rbf(untag_sum(v[1].x, v[3].x)), 1.f + rbf(untag_sum(v[1].y, v[3].y))));
        sts1(d + 16, pack_bf(1.f + rbf(untag_sum(v[1].z, v[3].z)), 1.f + rbf(untag_sum(v[1].w, v[3].w))));
        sts1(d + 8, pack_bf(untag_sum(v[0].x, v[2].x), untag_sum(v[0].y, v[2].y)));
        sts1(d + 24, pack_bf(untag_sum(v[0].z, v[2].z), untag_sum(v[0].w, v[2].w)));
        if (wg == 0) {
          uint32_t n = 0;
          while (((s0.x ^ tag) | (s0.y ^ tag)) & 3u) { s0 = ld_relaxed2(g_ln1 + (rb * 128 + tid) * 4); watchdog(n); }
          uint32_t ih, il;
          split_inv(bf_hi(s0.y), ih, il);
          sts4(stage + 4096 + tid * 16, make_uint4(__byte_perm(s0.x, 0, 0x3232), ih, il, 0));
        }
        mbar_arrive(bar_mod);
      }
      cluster_wait();
      if (wg == 1) bar_arrive(2, 256);
      mbar_wait(bar_mod, 0);
      PROF(1, tid == 0, 2);
    }

    float f0 = 0.f, f1 = 0.f;
    const uint32_t rempty = lane < 2 ? mapa(bempty, lane & 1) : 0;
    constexpr uint32_t GE = NSLOT * 8 + 32;
    float o[64], s[64];
#pragma unroll 1
    for (int ps = 0; ps < 3; ps++) {
      {
        const uint32_t xt = ps == 1 ? XT1 : XT2, wt = ps == 1 ? WT1 : WT2;
        const int nst = ps == 2 ? 28 : 14;
        if (ps == 0) {
          float ga[64], gb[64];
#pragma unroll
          for (int i = 0; i < 64; i++) { ga[i] = 0.f; gb[i] = 0.f; }
          uint32_t a[2][16];
          const uint32_t l = fresh_lane();
          const uint4 r0 = lds4(stage + 4096 + (warp * 16 + (l >> 2)) * 16), r1 = lds4(stage + 4096 + 128 + (warp * 16 + (l >> 2)) * 16);
          auto transform = [&](int i, uint32_t (&f)[16], uint32_t z) {
            const uint32_t ad = base + (i & 3) * GST_BYTES + wg * 8192 + frag_offset(warp) + z;
            mbar_wait(xfull + (i & 3) * 8, i >> 2);
#pragma unroll
            for (int kk = 0; kk < 4; kk++) ldmatrix4(ad ^ (kk * 32), f[4 * kk], f[4 * kk + 1], f[4 * kk + 2], f[4 * kk + 3]);
#pragma unroll
            for (int kk = 0; kk < 4; kk++) {
              const uint4 m = lds4(stage + (l & 3) * 16 + ((2 * cj + i) & 15) * 256 + kk * 64);
              f[4 * kk] = ln_mod(f[4 * kk], r0.x, r0.y, r0.z, m.x, m.z);
              f[4 * kk + 1] = ln_mod(f[4 * kk + 1], r1.x, r1.y, r1.z, m.x, m.z);
              f[4 * kk + 2] = ln_mod(f[4 * kk + 2], r0.x, r0.y, r0.z, m.y, m.w);
              f[4 * kk + 3] = ln_mod(f[4 * kk + 3], r1.x, r1.y, r1.z, m.y, m.w);
            }
            keep(f);
            mbar_arrive_pred(xempty + (i & 3) * 8, l == 0);
          };
          auto publish = [&](int u, uint32_t (&f)[16]) {
            const uint32_t sc = stage + 8192 + wg * 8192;
#pragma unroll
            for (int kk = 0; kk < 4; kk++) stmatrix4((sc + frag_offset(warp)) ^ (kk * 32), f[4 * kk], f[4 * kk + 1], f[4 * kk + 2], f[4 * kk + 3]);
            __syncwarp();
            const uint32_t src = sc + (warp & 3) * 2048 + l * 16;
            uint8_t* dst = g_act + (uint32_t)(rb * 80 + cj * 2 + u) * UNIT + warp * 2048 + l * 16;
#pragma unroll
            for (int p4 = 0; p4 < 4; p4++) stg4(dst + p4 * 512, lds4(src + p4 * 512));
            __syncwarp();
            if (u == 1) mbar_arrive_pred(bar_hpub, l == 0);
          };
          auto multiply = [&](int i, uint32_t (&f)[16]) {
            mbar_wait(gfull + (i & 3) * 8, i >> 2);
            const uint64_t db = make_desc(base + (i & 3) * GST_BYTES + UNIT, 8192, 1024);
            wg_fence();
#pragma unroll
            for (int kk = 0; kk < 4; kk++) mma256_rs(ga, gb, f[4 * kk], f[4 * kk + 1], f[4 * kk + 2], f[4 * kk + 3], db + kk * 128);
            wg_commit();
          };
          transform(0, a[0], 0); publish(0, a[0]); transform(1, a[1], 0); multiply(0, a[0]); publish(1, a[1]);
#pragma unroll
          for (int i = 1; i < NRS; i++) {
            if (i >= 2) {
              uint32_t z = r0.w;
#pragma unroll
              for (int k = 0; k < 16; k += 2) asm volatile("lop3.b32 %0, %1, %2, %0, 0xA8;" : "+r"(z) : "r"(a[i & 1][k]), "r"(a[i & 1][k + 1]));
              transform(i, a[i & 1], z);
            }
            multiply(i, a[i & 1]);
            wg_wait<1>();
            mbar_arrive_cl(rempty, GE + ((i + 3) & 3) * 8);
          }
          mbar_arrive_pred(bar_pread, l == 0);
#pragma unroll 1
          for (int i = NRS; i < 14; i++) {
            mbar_wait(xfull + (i & 3) * 8, (i >> 2) & 1);
            mbar_wait(gfull + (i & 3) * 8, (i >> 2) & 1);
            const uint32_t xa = base + (i & 3) * GST_BYTES;
            const uint64_t da = make_desc(xa + wg * 8192, 16, 1024), db = make_desc(xa + UNIT, 8192, 1024);
            if (i == 13) bar_sync(2 + wg, 256);
            wg_fence();
#pragma unroll
            for (int kk = 0; kk < 4; kk++) mma256_ss(ga, gb, da + kk * 2, db + kk * 128, 1);
            wg_commit();
            if (i == 13) bar_arrive(3 - wg, 256);
            wg_wait<1>();
            uint32_t z = r0.w;
#pragma unroll
            for (int k = 0; k < 16; k += 2) asm volatile("lop3.b32 %0, %1, %2, %0, 0xA8;" : "+r"(z) : "r"(a[1][k]), "r"(a[1][k + 1]));
            mbar_arrive_cl(rempty, GE + ((i + 3) & 3) * 8 + z);
            mbar_arrive_pred(xempty + ((i + 3) & 3) * 8, l == 0 && i != NRS);
          }
          mbar_wait(xfull + 16, 1);
          mbar_wait(xfull + 24, 1);
          wg_wait<0>();
          keep(ga); keep(gb);
#pragma unroll
          for (int i = 0; i < 64; i++) {
            asm volatile("mov.b32 %0, %1;" : "=f"(s[i]) : "f"(ga[i]));
            asm volatile("mov.b32 %0, %1;" : "=f"(o[i]) : "f"(gb[i]));
          }
        } else {
          float ga[64], gb[64];
#pragma unroll
          for (int i = 0; i < 64; i++) {
            asm volatile("mov.b32 %0, %1;" : "=f"(ga[i]) : "f"(s[i]));
            asm volatile("mov.b32 %0, %1;" : "=f"(gb[i]) : "f"(o[i]));
          }
#pragma unroll 1
          for (int i = 0; i < nst; i++) {
            mbar_wait(gfull + (i & 3) * 8, (i >> 2) & 1);
            const uint64_t da = make_desc(base + unit_of(xt, i & 3) + wg * 8192, 16, 1024), db = make_desc(base + unit_of(wt, i & 3), 8192, 1024);
            if (i == nst - 1) bar_sync(2 + wg, 256);
            wg_fence();
#pragma unroll
            for (int kk = 0; kk < 4; kk++) mma256_ss(ga, gb, da + kk * 2, db + kk * 128, kk ? 1 : i);
            wg_commit();
            if (i == nst - 1) bar_arrive(3 - wg, 256);
            wg_wait<1>();
            mbar_arrive_cl(rempty, GE + ((i + 3) & 3) * 8, i != 0);
            PROF(4, tid == 0 && (i & 3) == 0, 40 + (ps - 1) * 4 + i / 4);
          }
          wg_wait<0>();
          keep(ga); keep(gb);
#pragma unroll
          for (int i = 0; i < 64; i++) {
            asm volatile("mov.b32 %0, %1;" : "=f"(s[i]) : "f"(ga[i]));
            asm volatile("mov.b32 %0, %1;" : "=f"(o[i]) : "f"(gb[i]));
          }
        }
        mbar_arrive_cl(rempty, GE + (ps == 2 ? 24 : 8));
        if (ps == 2) break;
      }
      const uint32_t qw = base + wg * 8192, qt = QT >> (16 * ps), at = ps ? AT1 : AT0;
      {
        const uint32_t wt = ps ? WT1 : WT0;
        const uint64_t da0 = make_desc(qw + unit_of(qt, 2), 16, 1024), da1 = make_desc(qw + unit_of(qt, 3), 16, 1024);
        const uint64_t db0 = make_desc(base + unit_of(wt, 2), 8192, 1024), db1 = make_desc(base + unit_of(wt, 3), 8192, 1024);
        mbar_wait(gfull + 16, 1);
        mbar_wait(gfull + 24, 1);
        bar_sync(2 + wg, 256);
        wg_fence();
#pragma unroll
        for (int kk = 0; kk < 8; kk++) mma_ss<1>(s, (kk < 4 ? da0 : da1) + (kk & 3) * 2, (kk < 4 ? db0 : db1) + (kk & 3) * 128, 1);
        wg_commit();
        bar_arrive(3 - wg, 256);
        mbar_wait(ps == 0 ? bar_pread : bar_ofree + 8, 0);
        mbar_wait(bfull, 0);
        wg_wait<0>();
        keep(s);
        PROF(2, tid == 0, 8 + ps * 8);
        store_chunk<0>(s, qw + unit_of(qt, 0) + frag_offset(warp));
        store_chunk<1>(s, qw + unit_of(qt, 1) + frag_offset(warp));
        fence_async_smem();
        bar_sync(2 + wg, 256);
        wg_fence();
        issue_qk(s, qw + unit_of(qt, 0), qw + unit_of(qt, 1), base + unit_of(at, 0));
        wg_commit();
#pragma unroll
        for (int kk = 0; kk < 8; kk++) mma_ss<1>(o, (kk < 4 ? da0 : da1) + (kk & 3) * 2, (kk < 4 ? db0 : db1) + UNIT / 16 + (kk & 3) * 128, 1);
        wg_commit();
        bar_arrive(3 - wg, 256);
        wg_wait<1>();
        keep(s);
        mbar_arrive_cl(rempty, 0);
      }
      PROF(4, tid == 0 && ps == 1, 61);
      float l0 = 0.25f, l1 = 0.25f;
      auto step = [&](auto odd_c, const int j, uint32_t (&pw)[32], uint32_t (&pr)[32]) {
        constexpr bool ODD = decltype(odd_c)::value;
        const bool first = !ODD && (j & 2) == 0, last = ODD && j == 7;
        const uint32_t ph = (j >> 1) & 1;
        float i0, i1, a0, a1;
        if (first) { i0 = inv_quad_sum(l0); i1 = inv_quad_sum(l1); l0 = 0.f; l1 = 0.f; }
        bool redo = !ODD && (j | ps) == 0, again = false;
        while (true) {
          if (redo) {
            float m0 = fmaxf(s[0], s[1]), m1 = fmaxf(s[2], s[3]);
#pragma unroll
            for (int i = 1; i < 16; i++) { m0 = fmaxf(m0, fmaxf(s[4 * i], s[4 * i + 1])); m1 = fmaxf(m1, fmaxf(s[4 * i + 2], s[4 * i + 3])); }
            m0 = fmaxf(m0, __shfl_xor_sync(0xffffffffu, m0, 1)); m1 = fmaxf(m1, __shfl_xor_sync(0xffffffffu, m1, 1));
            m0 = fmaxf(m0, __shfl_xor_sync(0xffffffffu, m0, 2)); m1 = fmaxf(m1, __shfl_xor_sync(0xffffffffu, m1, 2));
            m0 *= SCL2; m1 *= SCL2;
            if (!first) {
              m0 = fmaxf(m0, f0); m1 = fmaxf(m1, f1);
              const float c0 = ex2(f0 - m0), c1 = ex2(f1 - m1);
              l0 *= c0; l1 *= c1;
              wg_wait<0>();
              keep(o);
#pragma unroll
              for (int i = 0; i < 16; i++) { o[4 * i] *= c0; o[4 * i + 1] *= c0; o[4 * i + 2] *= c1; o[4 * i + 3] *= c1; }
            }
            f0 = m0; f1 = m1;
          }
          float b0 = 0.f, b1 = 0.f;
          a0 = 0.f; a1 = 0.f;
#pragma unroll
          for (int i = 0; i < 16; i++) {
            const float e0 = ex2(fmaf(s[4 * i], SCL2, -f0)), e1 = ex2(fmaf(s[4 * i + 1], SCL2, -f0));
            const float e2 = ex2(fmaf(s[4 * i + 2], SCL2, -f1)), e3 = ex2(fmaf(s[4 * i + 3], SCL2, -f1));
            a0 += e0; b0 += e1; a1 += e2; b1 += e3;
            pw[2 * i] = pack_bf(e0, e1); pw[2 * i + 1] = pack_bf(e2, e3);
            if (i == VREL) {
#pragma unroll
              for (int k = 0; k < 2 * VREL + 2; k++) asm volatile("" : "+r"(pw[k])::"memory");
              mbar_wait(bfull + (ODD ? 24 : 8), ph);
              wg_wait<0>();
              mbar_arrive_cl(rempty, ODD ? 16 : (j ? 0 : GE + 16), !again);
              if (!ODD) mbar_arrive_cl(rempty, GE + 24, !again && j == 0);
#pragma unroll
              for (int k = 4 * VREL + 4; k < 64; k++) asm volatile("" : "+f"(s[k])::"memory");
            }
          }
          a0 += b0; a1 += b1;
          if (redo) break;
          redo = __any_sync(0xffffffffu, !(a0 + a1 < 0x1p70f));
          if (first) {
            uint32_t m0 = __ballot_sync(0xffffffffu, a0 > 0x1p-50f), m1 = __ballot_sync(0xffffffffu, a1 > 0x1p-50f);
            m0 |= m0 >> 1; m1 |= m1 >> 1; m0 |= m0 >> 2; m1 |= m1 >> 2;
            redo = redo || (m0 & m1 & 0x11111111u) != 0x11111111u;
          }
          if (!redo) break;
          again = true;
        }
        l0 += a0; l1 += a1;
        keep(pw);
        keep(o);
        const uint32_t qo = qt >> (j ? 0 : 8);
        if (first) store_chunk<0>(o, i0, i1, qw + unit_of(qo, 0) + frag_offset(warp));
        keep(o);
        bar_sync(2 + wg, 256);
        if (!last) {
          const uint32_t qn = qt >> (j >= 3 ? 8 : 0);
          wg_fence();
          issue_qk(s, qw + unit_of(qn, 0), qw + unit_of(qn, 1), base + unit_of(at, ODD ? 3 : 1));
          wg_commit();
          mbar_wait(bfull + (ODD ? 0 : 16), ODD ? ph ^ 1 : ph);
        }
        if (first) { store_chunk<1>(o, i0, i1, qw + unit_of(qo, 1) + frag_offset(warp)); keep(o); }
        wg_fence();
        issue_pv(o, pw, base + unit_of(at, ODD ? (last ? 3 : 0) : 2), !first);
        wg_commit();
        bar_arrive(3 - wg, 256);
        if (first) { fence_async_smem(); mbar_arrive_pred(bar_ofull + wg * 8, j); PROF(2, tid == 0 && j, 9 + ps * 8); }
        wg_wait<1>();
        keep(s);
        mbar_arrive_cl(rempty, ODD ? 24 : 8, !last);
        PROF(4, tid == 0 && ps == 1, 51 + j);
      };
      uint32_t pa[32], pb[32];
#pragma unroll 1
      for (int j = 0; j < 8; j += 2) {
        step(std::false_type{}, j, pa, pb);
        step(std::true_type{}, j + 1, pb, pa);
      }
      {
        const float i0 = inv_quad_sum(l0), i1 = inv_quad_sum(l1);
        wg_wait<0>();
        keep(o);
        mbar_arrive_cl(rempty, 24);
        store_chunk<0>(o, i0, i1, qw + unit_of(qt, 2) + frag_offset(warp));
        store_chunk<1>(o, i0, i1, qw + unit_of(qt, 3) + frag_offset(warp));
        fence_async_smem();
        mbar_arrive(bar_ofull + wg * 8);
      }
      PROF(2, tid == 0, 10 + ps * 8);
    }

    const int ln = fresh_lane(), g = ln >> 2, tq = ln & 3, ct = warp * 32 + ln;
    const bool lane0 = ln == 0;
    const int lrow0 = warp * 16 + g;
    const int grow0 = rb * 128 + lrow0;
    const uint32_t res = base + OFF_RES, trow = res + wg * 8192 + frag_offset(warp);
    uint32_t xr[32];
    uint4 sv[4];
    const uint32_t* sp = g_stats + ((size_t)(tq >> 1) * 4 * SEQ + grow0 + (tq & 1) * 8) * 4;
    {
      const uint64_t da = make_desc(base + wg * 8192, 16, 1024), db = make_desc(base, 8192, 1024);
      constexpr int U = UNIT / 16;
#define HALF_STAGE(acc, xu, wu) _Pragma("unroll") for (int kk = 0; kk < 4; kk++) mma_ss<1>(acc, da + (xu) * U + kk * 2, db + (wu) * U + kk * 128, 1)
      PROF(10, ct == PT, 19); STAMP(0);
      cluster_arrive();
      mbar_wait(gfull, 1);
      mbar_wait(gfull + 8, 1);
      bar_sync(2 + wg, 256);
      wg_fence();
      HALF_STAGE(o, 6, 8);
      HALF_STAGE(o, 9, 11);
      wg_commit();
      STAMP(16);
      mbar_wait(gfull + 16, 1);
      STAMP(17);
      wg_fence();
      HALF_STAGE(o, 12, 1);
      wg_commit();
      bar_arrive(3 - wg, 256);
      mbar_wait(bar_par, 0);
      uint32_t* xo = g_xch + ((size_t)b * 8 * 256 + ct) * 4;
      const uint32_t* xi = g_xch + ((size_t)(b ^ 2) * 8 * 256 + ct) * 4;
      const uint32_t par1 = (~lds1(par + PAR_CONST + 4) & 1) << 16;
      wg_wait<0>();
      keep(o);
      mbar_arrive_pred(bar_ring, lane0);
      PROF(8, ct == PT, 20); STAMP(1);
#define SEND(i) st_b128(xo + (i) * 1024, (pack_bf(o[8 * (i)], o[8 * (i) + 1]) & ~0x10000u) | par1, pack_bf(o[8 * (i) + 2], o[8 * (i) + 3]), \
                        pack_bf(o[8 * (i) + 4], o[8 * (i) + 5]), pack_bf(o[8 * (i) + 6], o[8 * (i) + 7]))
#pragma unroll
      for (int i = 0; i < NS1; i++) SEND(i);
      PROF(8, ct == PT, 21); STAMP(2);
      bar_sync(2 + wg, 256);
      wg_fence();
      HALF_STAGE(s, 6, 7);
      HALF_STAGE(s, 9, 10);
      HALF_STAGE(s, 12, 0);
      wg_commit();
      bar_arrive(3 - wg, 256);
      STAMP(18);
      mbar_wait(gfull + 24, 1);
#pragma unroll
      for (int i = NS1; i < 8; i++) SEND(i);
      uint4 v[8];
#pragma unroll
      for (int i = 0; i < 4; i++) v[i] = ld_b128(xi + i * 1024);
      STAMP(19);
      mbar_wait(bar_rx, 0);
      wg_wait<0>();
      mbar_arrive_pred(bar_ring + 8, lane0);
      bar_sync(2 + wg, 256);
      STAMP(20);
#pragma unroll
      for (int i = 4; i < 8; i++) v[i] = ld_b128(xi + i * 1024);
      mbar_wait(bar_xres, 0);
      wg_fence();
      HALF_STAGE(s, 13, 2);
      HALF_STAGE(s, 8, 3);
      wg_commit();
      bar_arrive(3 - wg, 256);
      STAMP(21);
      wg_wait<0>();
      keep(s);
      mbar_arrive_pred(bar_ring + 16, lane0);
      PROF(10, ct == PT, 23); STAMP(4);
#pragma unroll
      for (int i = 0; i < 16; i += 2) ldmatrix4((trow ^ ((i & 7) << 4)) + (i >> 3) * 16384, xr[2 * i], xr[2 * i + 1], xr[2 * i + 2], xr[2 * i + 3]);
      {
        uint32_t n = 0;
        bool ok;
        do {
          ok = true;
#pragma unroll
          for (int i = 0; i < 8; i++)
            if ((v[i].x & 0x10000u) != par1) { v[i] = ld_b128(xi + i * 1024); ok = false; }
          watchdog(n);
        } while (!ok);
      }
      __syncwarp();
      PROF(8, ct == PT, 22); STAMP(3);
#pragma unroll
      for (int k = 0; k < 4; k++) sv[k] = ld_b128(sp + k * SEQ * 4);
      float ds[4] = {0.f, 0.f, 0.f, 0.f}, dl[4] = {0.f, 0.f, 0.f, 0.f}, q0[4] = {0.f, 0.f, 0.f, 0.f}, q1[4] = {0.f, 0.f, 0.f, 0.f};
#pragma unroll
      for (int i = 0; i < 8; i++) {
        const uint32_t ga0 = lds1(par + PAR_T2 + i * 128 + tq * 16 + 12), ga1 = lds1(par + PAR_T2 + i * 128 + 64 + tq * 16 + 12);
        const uint4 bw = lds4(par + PAR_T1 + i * 64 + tq * 16);
        const uint32_t u0 = hfma2(ga0, hadd2(pack_bf(s[8 * i], s[8 * i + 1]), v[i].x & ~0x10000u), xr[4 * i]);
        const uint32_t u1 = hfma2(ga0, hadd2(pack_bf(s[8 * i + 2], s[8 * i + 3]), v[i].y), xr[4 * i + 1]);
        const uint32_t u2 = hfma2(ga1, hadd2(pack_bf(s[8 * i + 4], s[8 * i + 5]), v[i].z), xr[4 * i + 2]);
        const uint32_t u3 = hfma2(ga1, hadd2(pack_bf(s[8 * i + 6], s[8 * i + 7]), v[i].w), xr[4 * i + 3]);
        xr[4 * i] = u0; xr[4 * i + 1] = u1; xr[4 * i + 2] = u2; xr[4 * i + 3] = u3;
        mma16816(ds, u0, u1, u2, u3, (g & 1) ? bw.x : 0x3f803f80u, (g & 1) ? bw.y : 0x3f803f80u);
        mma16816(dl, u0, u1, u2, u3, bw.z, bw.w);
        mma16816(q0, u0, u1, u2, u3, u0, u2);
        mma16816(q1, u0, u1, u2, u3, u1, u3);
      }
      const float sqa = __shfl_sync(0xffffffffu, (g & 1) ? q0[1] : q0[0], g * 4 + (g >> 1));
      const float sqb = __shfl_sync(0xffffffffu, (g & 1) ? q1[3] : q1[2], g * 4 + (g >> 1));
      const uint4 own = (tq & 1) ? make_uint4(__float_as_uint(ds[2]), __float_as_uint(sqb), __float_as_uint(ds[3] + dl[3]), tag)
                                 : make_uint4(__float_as_uint(ds[0]), __float_as_uint(sqa), __float_as_uint(ds[1] + dl[1]), tag);
      if ((tq >> 1) == (cj >> 2)) {
        st_b128(const_cast<uint32_t*>(sp) + (cj & 3) * SEQ * 4, own.x, own.y, own.z, own.w);
#pragma unroll
        for (int k = 0; k < 4; k++) if (k == (cj & 3)) sv[k] = own;
      }
    }
    PROF(8, ct == PT, 29); STAMP(5);
    uint32_t mm, ih, il;
    float rbest;
    uint32_t wf[128];
    const uint32_t frow = (ln & 7) + (ln >> 4) * 8;
    const uint32_t wfo = base + (warp & 1) * 8192 + frow * 64 + ((((ln >> 3) & 1) ^ ((frow >> 1) & 3)) << 4);
#define LOAD_WF(m) _Pragma("unroll") for (int f = 0; f < 16; f++) {                                                   \
      const int r = ((f >> 1) * 4 + (m) * 2 + (f & 1)) * 4;                                                           \
      ldmatrix4t(((wfo + unit_of((m) ? FT_U : FT_G, warp >> 1)) ^ ((f & 1) * 32)) + (f >> 1) * 1024, wf[r], wf[r + 1], wf[r + 2], wf[r + 3]); \
    }
    bool early;
    {
      uint4 v0 = sv[0], v1 = sv[1], v2 = sv[2], v3 = sv[3];
      const bool wait1 = __any_sync(0xffffffffu, v0.w != tag || v1.w != tag || v2.w != tag || v3.w != tag);
      if (v0.w != tag) v0 = ld_b128(sp);
      if (v1.w != tag) v1 = ld_b128(sp + SEQ * 4);
      if (v2.w != tag) v2 = ld_b128(sp + SEQ * 8);
      if (v3.w != tag) v3 = ld_b128(sp + SEQ * 12);
#pragma unroll
      for (int i = 0; i < 16; i += 2) stmatrix4((trow ^ ((i & 7) << 4)) + (i >> 3) * 16384, xr[2 * i], xr[2 * i + 1], xr[2 * i + 2], xr[2 * i + 3]);
      early = b >= NFFN || (wait1 && __all_sync(0xffffffffu, mbar_test(bar_box + (warp >> 1) * 8, 0)));
      if (early) {
        LOAD_WF(0);
        __syncwarp();
        mbar_arrive_pred(bar_gate, lane0);
      }
      const uint4 cst = lds4(par + PAR_CONST);
      const float A1 = __uint_as_float(cst.x), A2 = __uint_as_float(cst.z);
      uint32_t n = 0;
      while (v0.w != tag || v1.w != tag || v2.w != tag || v3.w != tag) {
        if (v0.w != tag) v0 = ld_b128(sp);
        if (v1.w != tag) v1 = ld_b128(sp + SEQ * 4);
        if (v2.w != tag) v2 = ld_b128(sp + SEQ * 8);
        if (v3.w != tag) v3 = ld_b128(sp + SEQ * 12);
        watchdog(n);
      }
      __syncwarp();
      PROF(8, ct == PT, 30); STAMP(6);
      float su = (__uint_as_float(v0.x) + __uint_as_float(v1.x)) + (__uint_as_float(v2.x) + __uint_as_float(v3.x));
      float sq = (__uint_as_float(v0.y) + __uint_as_float(v1.y)) + (__uint_as_float(v2.y) + __uint_as_float(v3.y));
      float dt = (__uint_as_float(v0.z) + __uint_as_float(v1.z)) + (__uint_as_float(v2.z) + __uint_as_float(v3.z));
      su += __shfl_xor_sync(0xffffffffu, su, 2); sq += __shfl_xor_sync(0xffffffffu, sq, 2); dt += __shfl_xor_sync(0xffffffffu, dt, 2);
      const float m = su * (1.f / DM);
      float mb, sd;
      ln_scalars(m, fmaxf(sq * (1.f / DM) - m * m, 0.f), mb, sd);
      const float inv = rcp(sd);
      rbest = (dt - mb * A1) * inv + A2;
      mm = pack_bf(mb, mb);
      ih = pack_bf(inv, inv);
      const float lo = inv - bf_lo(ih);
      il = pack_bf(lo, lo);
    }
    int ibest;
    {
      const uint32_t bits = __float_as_uint(rbest);
      const uint32_t key = (((int)bits < 0 ? ~bits : bits | 0x80000000u) & ~0x1ffu) | ((127 - lrow0 - (tq & 1) * 8) << 2) | tag;
      sts1(par + PAR_RED + warp * 4, __reduce_max_sync(0xffffffffu, key));
      PROF(8, ct == PT, 38); STAMP(7);
      bar_sync(1, 256);
      const uint4 ka = lds4(par + PAR_RED), kb = lds4(par + PAR_RED + 16);
      const uint32_t k2 = max(max(max(ka.x, ka.y), max(ka.z, ka.w)), max(max(kb.x, kb.y), max(kb.z, kb.w)));
      if (ct == 0 && (cj & CWM) == 0) st_relaxed(g_cand + rb, k2);
      ibest = 127 - ((k2 >> 2) & 127);
    }
    PROF(8, ct == PT, 39); STAMP(8);
    if ((ibest >> 4) == warp) {
      const int src = (ibest & 7) * 4 + ((ibest >> 3) & 1), ch = g * 2;
      const uint32_t cm = __shfl_sync(0xffffffffu, mm, src), ch_ = __shfl_sync(0xffffffffu, ih, src), cl = __shfl_sync(0xffffffffu, il, src);
      const uint32_t xa = res + (ch >> 3) * 16384 + ibest * 128 + (((ch & 7) ^ (ibest & 7)) << 4) + tq * 4;
      const uint32_t x0 = lds1(xa), x1 = lds1(xa ^ 16);
      const uint2 p0 = lds2(par + PAR_T2 + ch * 64 + tq * 16), p1 = lds2(par + PAR_T2 + ch * 64 + 64 + tq * 16);
      uint32_t* dst = g_row + rb * 2 * DM + cj * 128 + ln * 4;
      st_pairs(dst, ln_mod(x0, cm, ch_, cl, p0.x, p0.y), ln_mod(x1, cm, ch_, cl, p1.x, p1.y), tag);
      st_pairs(dst + DM, x0, x1, tag);
      __syncwarp();
    }
    PROF(8, ct == PT, 37); STAMP(9);
    uint32_t wd[64];
    const uint32_t wda = base + unit_of(FT_D, warp >> 1) + (warp & 1) * 8192 + frow * 128 + ((((ln >> 3) & 1) ^ (ln & 7)) << 4);
#define LOAD_WD(f) ldmatrix4t((wda ^ ((((f) >> 1) & 3) * 32)) + ((f) >> 3) * 4096 + ((f) & 1) * 2048, wd[4 * (f)], wd[4 * (f) + 1], wd[4 * (f) + 2], wd[4 * (f) + 3])
    if (!early) {
      mbar_wait(bar_box + (warp >> 1) * 8, 0);
      LOAD_WF(0);
      __syncwarp();
      mbar_arrive_pred(bar_gate, lane0);
    }
    if (b < NFFN) {
      const uint32_t own = base + unit_of(FT_G, warp >> 1) + (warp & 1) * 8192;
      mbar_wait(bar_box + (4 + (warp >> 1)) * 8, 0);
      LOAD_WF(1);
      uint32_t* const ydst = g_ypart + ((size_t)(warp * 16 + tq * 2) * NFFN + b) * 8 + g;
      PROF(8, ct == PT, 31); STAMP(10);
      mbar_wait(bar_box + (8 + (warp >> 1)) * 8, 0);
#pragma unroll
      for (int f = 0; f < WDE; f++) LOAD_WD(f);
      STAMP(11);
      mbar_wait(bar_sel, 0);
      PROF(8, ct == PT, 33); STAMP(12);
      float d[8][4];
#pragma unroll
      for (int i = 0; i < 4; i++) { d[i][0] = 0.f; d[i][1] = 0.f; d[i][2] = 0.f; d[i][3] = 0.f; }
#pragma unroll
      for (int ks = 0; ks < 8; ks++) {
        const uint2 hb = lds2(own + 256 + ks * 32 + tq * 8);
#pragma unroll
        for (int mt = 0; mt < 4; mt++) {
          const int r = ks * 16 + mt * 4;
          mma16816(d[mt], wf[r], wf[r + 1], wf[r + 2], wf[r + 3], hb.x, hb.y);
        }
      }
      sts2(own + (tq * 8 + g) * 8, __float_as_uint((tq & 2) ? ((tq & 1) ? d[1][2] : d[1][0]) : ((tq & 1) ? d[0][2] : d[0][0])),
           __float_as_uint((tq & 2) ? ((tq & 1) ? d[3][2] : d[3][0]) : ((tq & 1) ? d[2][2] : d[2][0])));
      bar_sync(1, 256);
      uint32_t ab[4];
      {
        float G = 0.f, U = 0.f;
        uint2 pv[8];
#pragma unroll
        for (int w8 = 0; w8 < 8; w8++) pv[w8] = lds2(base + ln * 8 + ((FT_G >> (w8 >> 1) * 4) & 15) * UNIT + (w8 & 1) * 8192);
#pragma unroll
        for (int w8 = 0; w8 < 8; w8 += 2) {
          G += __uint_as_float(pv[w8].x) + __uint_as_float(pv[w8 + 1].x);
          U += __uint_as_float(pv[w8].y) + __uint_as_float(pv[w8 + 1].y);
        }
#pragma unroll
        for (int f = WDE; f < 16; f++) LOAD_WD(f);
        const float act = rbf(silu_f(rbf(G))) * rbf(U);
        const uint32_t pk = pack_bf(act, __shfl_down_sync(0xffffffffu, act, 1));
#pragma unroll
        for (int i = 0; i < 4; i++) ab[i] = __shfl_sync(0xffffffffu, pk, i * 8 + tq * 2);
      }
      PROF(8, ct == PT, 34); STAMP(13);
#pragma unroll
      for (int mt = 0; mt < 8; mt++) {
        d[mt][0] = 0.f; d[mt][1] = 0.f; d[mt][2] = 0.f; d[mt][3] = 0.f;
        mma16816(d[mt], wd[mt * 8], wd[mt * 8 + 1], wd[mt * 8 + 2], wd[mt * 8 + 3], ab[0], ab[1]);
        mma16816(d[mt], wd[mt * 8 + 4], wd[mt * 8 + 5], wd[mt * 8 + 6], wd[mt * 8 + 7], ab[2], ab[3]);
      }
#pragma unroll
      for (int i = 0; i < 4; i++) {
        const int m4 = (i >> 1) * 4, e = (i & 1) * 2;
        const float y = (tq & 2) ? ((tq & 1) ? d[m4 + 3][e] : d[m4 + 2][e]) : ((tq & 1) ? d[m4 + 1][e] : d[m4][e]);
        st_relaxed(ydst + (m4 * 2 + (i & 1)) * NFFN * 8, tagf(y, tag));
      }
      PROF(8, ct == PT, 35); STAMP(14);
    }
    mbar_wait(bar_sel, 0);
    mbar_arrive_pred(bar_win, ct == 0);
    const int iwin = lds1(par + PAR_CONST + 60) & 0x7ff;
    {
      const uint32_t mm0 = __shfl_sync(0xffffffffu, mm, ln & ~1), mm1 = __shfl_sync(0xffffffffu, mm, ln | 1);
      const uint32_t ih0 = __shfl_sync(0xffffffffu, ih, ln & ~1), ih1 = __shfl_sync(0xffffffffu, ih, ln | 1);
      const uint32_t il0 = __shfl_sync(0xffffffffu, il, ln & ~1), il1 = __shfl_sync(0xffffffffu, il, ln | 1);
      const bool mine = (iwin >> 4) == rb * 8 + warp;
#pragma unroll 1
      for (int hf = 0; hf < 2; hf++) {
        uint32_t x[16];
#pragma unroll
        for (int i = 0; i < 8; i += 2) ldmatrix4((trow ^ (i << 4)) + hf * 16384, x[2 * i], x[2 * i + 1], x[2 * i + 2], x[2 * i + 3]);
#pragma unroll
        for (int i = 0; i < 8; i++) {
          const uint4 pv = lds4(par + PAR_T2 + (hf * 8 + i) * 64 + tq * 16);
          x[2 * i] = hadd2(x[2 * i], hmul2(pv.z, ln_mod(x[2 * i], mm0, ih0, il0, pv.x, pv.y)));
          x[2 * i + 1] = hadd2(x[2 * i + 1], hmul2(pv.z, ln_mod(x[2 * i + 1], mm1, ih1, il1, pv.x, pv.y)));
        }
        if (mine) {
          uint32_t* dst = reinterpret_cast<uint32_t*>(P.out + (size_t)grow0 * DM + cj * 128 + hf * 64) + tq;
#pragma unroll
          for (int i = 0; i < 8; i++) {
            if (grow0 != iwin) dst[i * 4] = x[2 * i];
            if (grow0 + 8 != iwin) dst[i * 4 + 4 * DM] = x[2 * i + 1];
          }
        } else {
#pragma unroll
          for (int i = 0; i < 8; i += 2) stmatrix4((trow ^ (i << 4)) + hf * 16384, x[2 * i], x[2 * i + 1], x[2 * i + 2], x[2 * i + 3]);
          fence_async_smem();
          __syncwarp();
          if (elect_one()) {
            tma2d_store(&maps.out, res + hf * 16384 + warp * 2048, cj * 128 + hf * 64, rb * 128 + warp * 16);
            asm volatile("cp.async.bulk.commit_group;" ::: "memory");
          }
        }
      }
      asm volatile("cp.async.bulk.wait_group.read 0;" ::: "memory");
    }
    PROF(8, ct == PT, 11); STAMP(15);
    cluster_wait();
  }
}

typedef CUresult (*EncodeFn)(CUtensorMap*, CUtensorMapDataType, cuuint32_t, void*, const cuuint64_t*, const cuuint64_t*,
                             const cuuint32_t*, const cuuint32_t*, CUtensorMapInterleave, CUtensorMapSwizzle,
                             CUtensorMapL2promotion, CUtensorMapFloatOOBfill);

void map2d(EncodeFn enc, CUtensorMap* m, const void* p, uint64_t rows, uint64_t cols, uint32_t brows) {
  cuuint64_t dims[2] = {cols, rows}, strides[1] = {cols * 2};
  cuuint32_t box[2] = {64, brows}, es[2] = {1, 1};
  enc(m, CU_TENSOR_MAP_DATA_TYPE_BFLOAT16, 2, const_cast<void*>(p), dims, strides, box, es, CU_TENSOR_MAP_INTERLEAVE_NONE,
      CU_TENSOR_MAP_SWIZZLE_128B, CU_TENSOR_MAP_L2_PROMOTION_L2_256B, CU_TENSOR_MAP_FLOAT_OOB_FILL_NONE);
}
void map2d_narrow(EncodeFn enc, CUtensorMap* m, const void* p, uint64_t rows, uint64_t cols) {
  cuuint64_t dims[2] = {cols, rows}, strides[1] = {cols * 2};
  cuuint32_t box[2] = {32, 256}, es[2] = {1, 1};
  enc(m, CU_TENSOR_MAP_DATA_TYPE_BFLOAT16, 2, const_cast<void*>(p), dims, strides, box, es, CU_TENSOR_MAP_INTERLEAVE_NONE,
      CU_TENSOR_MAP_SWIZZLE_64B, CU_TENSOR_MAP_L2_PROMOTION_L2_64B, CU_TENSOR_MAP_FLOAT_OOB_FILL_NONE);
}
void map3d(EncodeFn enc, CUtensorMap* m, const void* p, uint64_t rows, uint64_t cols, uint32_t brows, uint32_t nch) {
  cuuint64_t dims[3] = {64, rows, cols / 64}, strides[2] = {cols * 2, 128};
  cuuint32_t box[3] = {64, brows, nch}, es[3] = {1, 1, 1};
  enc(m, CU_TENSOR_MAP_DATA_TYPE_BFLOAT16, 3, const_cast<void*>(p), dims, strides, box, es, CU_TENSOR_MAP_INTERLEAVE_NONE,
      CU_TENSOR_MAP_SWIZZLE_128B, CU_TENSOR_MAP_L2_PROMOTION_L2_256B, CU_TENSOR_MAP_FLOAT_OOB_FILL_NONE);
}

}

extern "C" void kernel_launch(void* const* d_in, const int* in_sizes, int n_in, void* d_out, int out_size) {
  (void)in_sizes; (void)n_in; (void)out_size;
  static EncodeFn enc = nullptr;
  if (!enc) {
    void* fn = nullptr;
    cudaDriverEntryPointQueryResult st;
    cudaGetDriverEntryPoint("cuTensorMapEncodeTiled", &fn, cudaEnableDefault, &st);
    enc = (EncodeFn)fn;
    cudaFuncSetAttribute(fused_kernel, cudaFuncAttributeMaxDynamicSharedMemorySize, SMEM_BYTES);
  }
  Maps maps;
  map2d(enc, &maps.x, d_in[0], SEQ, DM, 128);
  map2d(enc, &maps.out, d_out, SEQ, DM, 16);
  map3d(enc, &maps.wq, d_in[3], DM, NQ, 64, 2);
  map3d(enc, &maps.k, d_in[1], 4 * SK, 128, 128, 1);
  map3d(enc, &maps.v, d_in[2], 4 * SK, 128, 128, 1);
  map3d(enc, &maps.wo, d_in[4], NQ, DM, 64, 2);
  map2d_narrow(enc, &maps.wg, d_in[7], DM, FF);
  map2d_narrow(enc, &maps.wu, d_in[8], DM, FF);
  map3d(enc, &maps.wd, d_in[9], FF, DM, 32, 4);
  map2d_narrow(enc, &maps.wm, d_in[11], DM, NMOD);
  Ptrs p;
  p.x = (const __nv_bfloat16*)d_in[0];
  p.w_r = (const __nv_bfloat16*)d_in[6];
  p.w_gate = (const __nv_bfloat16*)d_in[7];
  p.w_up = (const __nv_bfloat16*)d_in[8];
  p.w_down = (const __nv_bfloat16*)d_in[9];
  p.c = (const __nv_bfloat16*)d_in[10];
  p.w_mod = (const __nv_bfloat16*)d_in[11];
  p.out = (__nv_bfloat16*)d_out;
  fused_kernel<<<NMAIN + NHELP, 384, SMEM_BYTES>>>(maps, p);
}
```

```cpp
#include <cuda_runtime.h>
#include <cuda_bf16.h>
#include <cuda.h>
#include <stdint.h>
#include <type_traits>

#define HD 1
#define HDX 2
#define XF 4
#define XE 32
#define XR 0
#define PF2 1
#define PF2T 4
#define NRS 6
#define FPACE 3
#define GOST 20
#define WB 2
#define WN 24
#define RES0 17
#define RES1 20
#define HU 32
#define NS1 6
#define PD0 40
#define PG0 31
#define PSL 0
#define CWM 7
#define WDE 16
#define CWL 1
#define CW0 0
#define VREL 7
#define E0 3

namespace {

constexpr int SEQ = 2048, DM = 1024, NQ = 4096, SK = 2048, WIN = 512, FF = 3584, NMOD = 6144;
constexpr int NMAIN = 128, NHELP = 4, NFFN = 112;
constexpr int NSLOT = 4, SLOT_BYTES = 32768, UNIT = 16384, GST_BYTES = 3 * UNIT;
constexpr uint32_t XT0 = 0x9630, XT1 = 0x54DC, XT2 = 0xDC96;
constexpr uint32_t WT0 = 0xA741, WT1 = 0x720A, WT2 = 0x20A7;
constexpr uint32_t AT0 = 0x7420, AT1 = 0x2C0A;
constexpr uint32_t QT = 0x549696DC;
constexpr int OFF_STAGE = 12 * UNIT;
constexpr uint32_t FT_G = 0x761B, FT_U = 0x0CA9, FT_D = 0x382D;
constexpr int OFF_RES = 4 * UNIT;
constexpr int OFF_PAR = 14 * UNIT;
constexpr int OFF_BAR = OFF_PAR + 2048 + 512;
constexpr int SMEM_BYTES = OFF_BAR + 512;
static_assert(SMEM_BYTES <= 232448, "smem");

constexpr int PAR_T1 = 0;
constexpr int PAR_T2 = 512;
constexpr int PAR_CONST = 1536;
constexpr int PAR_RED = 1600;
constexpr int PAR_SINK = 2176;

struct Maps {
  CUtensorMap x, wq, k, v, wo, wg, wu, wd, wm, out;
};
struct Ptrs {
  const __nv_bfloat16 *x, *w_r, *c, *w_mod, *w_gate, *w_up, *w_down;
  __nv_bfloat16* out;
};

__device__ __align__(1024) uint8_t g_act[16 * 80 * UNIT];
__device__ __align__(128) uint32_t g_mod[NMOD];
__device__ __align__(128) uint32_t g_modp[2 * 2 * DM];
__device__ __align__(128) uint32_t g_ln1[SEQ * 4];
__device__ __align__(128) uint32_t g_cnt_h[16 * 32];
__device__ __align__(128) uint32_t g_cnt_o[128 * 32];
__device__ __align__(128) uint32_t g_xch[NMAIN * 8 * 256 * 4];
__device__ __align__(128) uint32_t g_stats[8 * SEQ * 4];
__device__ __align__(128) uint32_t g_cand[32];
__device__ __align__(128) uint32_t g_row[16 * 2 * DM];
__device__ __align__(128) uint32_t g_ypart[NMAIN * NFFN * 8];
__device__ uint32_t g_epoch;

__device__ __forceinline__ uint32_t fresh_lane() { uint32_t l; asm volatile("mov.u32 %0, %%laneid;" : "=r"(l)); return l; }
__device__ __forceinline__ uint32_t frag_offset(int warp) {
  const uint32_t l = fresh_lane();
  return ((warp & 3) * 16 + (l & 15)) * 128 + (((l >> 4) ^ (l & 7)) << 4);
}
__device__ __forceinline__ bool elect_one() {
  uint32_t p;
  asm volatile("{ .reg .pred q; elect.sync _|q, 0xffffffff; selp.u32 %0, 1, 0, q; }" : "=r"(p));
  return p;
}
__device__ __forceinline__ uint32_t smem_u32(const void* p) { return (uint32_t)__cvta_generic_to_shared(p); }
__device__ __forceinline__ void mbar_init(uint32_t bar, uint32_t cnt) {
  asm volatile("mbarrier.init.shared::cta.b64 [%0], %1;" ::"r"(bar), "r"(cnt) : "memory");
}
__device__ __forceinline__ void mbar_expect_tx(uint32_t bar, uint32_t bytes) {
  asm volatile("mbarrier.arrive.expect_tx.shared::cta.b64 _, [%0], %1;" ::"r"(bar), "r"(bytes) : "memory");
}
__device__ __forceinline__ void mbar_arrive(uint32_t bar) {
  asm volatile("mbarrier.arrive.shared::cta.b64 _, [%0];" ::"r"(bar) : "memory");
}
__device__ __forceinline__ void mbar_arrive_pred(uint32_t bar, bool p) {
  asm volatile("{ .reg .pred p; setp.ne.b32 p, %1, 0; @p mbarrier.arrive.shared::cta.b64 _, [%0]; }" ::"r"(bar), "r"((int)p) : "memory");
}
__device__ __forceinline__ void mbar_arrive_cl(uint32_t bar, uint32_t off, bool p = true) {
  asm volatile("{ .reg .pred p, q; .reg .b32 a; setp.ne.b32 q, %2, 0; setp.ne.and.b32 p, %0, 0, q; add.u32 a, %0, %1; @p mbarrier.arrive.shared::cluster.b64 _, [a]; }"
               ::"r"(bar), "r"(off), "r"((int)p) : "memory");
}
__device__ __forceinline__ uint32_t mapa(uint32_t addr, uint32_t cta) {
  uint32_t r; asm("mapa.shared::cluster.u32 %0, %1, %2;" : "=r"(r) : "r"(addr), "r"(cta)); return r;
}
__device__ __forceinline__ void cluster_arrive() { asm volatile("barrier.cluster.arrive.relaxed.aligned;" ::: "memory"); }
__device__ __forceinline__ void cluster_wait() { asm volatile("barrier.cluster.wait.aligned;" ::: "memory"); }
__device__ __forceinline__ void watchdog(uint32_t& n) {
}
__device__ __forceinline__ void mbar_wait(uint32_t bar, uint32_t parity) {
  asm volatile("{\n.reg .pred p;\nWAIT_%=:\nmbarrier.try_wait.parity.shared::cta.b64 p, [%0], %1;\n@!p bra WAIT_%=;\n}" ::"r"(bar), "r"(parity) : "memory");
}
__device__ __forceinline__ bool mbar_test(uint32_t bar, uint32_t parity) {
  uint32_t ok;
  asm volatile("{\n.reg .pred p;\nmbarrier.test_wait.parity.shared::cta.b64 p, [%1], %2;\nselp.u32 %0, 1, 0, p;\n}" : "=r"(ok) : "r"(bar), "r"(parity) : "memory");
  return ok;
}
__device__ __forceinline__ uint64_t l2_stream() {
  uint64_t f; asm("createpolicy.fractional.L2::evict_first.b64 %0, 1.0;" : "=l"(f)); return f;
}
__device__ __forceinline__ void tma2d(uint32_t dst, const CUtensorMap* m, int c0, int c1, uint32_t bar) {
  asm volatile("cp.async.bulk.tensor.2d.shared::cluster.global.mbarrier::complete_tx::bytes.L2::cache_hint [%0], [%1, {%3, %4}], [%2], %5;"
               ::"r"(dst), "l"(m), "r"(bar), "r"(c0), "r"(c1), "l"(l2_stream()) : "memory");
}
__device__ __forceinline__ void tma3d_prefetch(const CUtensorMap* m, int c0, int c1, int c2) {
  asm volatile("cp.async.bulk.prefetch.tensor.3d.L2.global.tile [%0, {%1, %2, %3}];" ::"l"(m), "r"(c0), "r"(c1), "r"(c2) : "memory");
}
__device__ __forceinline__ void bulk_load(uint32_t dst, const void* src, uint32_t bytes, uint32_t bar) {
  asm volatile("cp.async.bulk.shared::cluster.global.mbarrier::complete_tx::bytes [%0], [%1], %2, [%3];" ::"r"(dst), "l"(src), "r"(bytes), "r"(bar) : "memory");
}
__device__ __forceinline__ void bulk_load_stream(uint32_t dst, const void* src, uint32_t bytes, uint32_t bar) {
  asm volatile("cp.async.bulk.shared::cluster.global.mbarrier::complete_tx::bytes.L2::cache_hint [%0], [%1], %2, [%3], %4;"
               ::"r"(dst), "l"(src), "r"(bytes), "r"(bar), "l"(l2_stream()) : "memory");
}
__device__ __forceinline__ void tma2d_store(const CUtensorMap* m, uint32_t src, int c0, int c1) {
  asm volatile("cp.async.bulk.tensor.2d.global.shared::cta.bulk_group [%0, {%2, %3}], [%1];" ::"l"(m), "r"(src), "r"(c0), "r"(c1) : "memory");
}
__device__ __forceinline__ void bulk_store(void* dst, uint32_t src, uint32_t bytes) {
  asm volatile("cp.async.bulk.global.shared::cta.bulk_group [%0], [%1], %2;" ::"l"(dst), "r"(src), "r"(bytes) : "memory");
}
__device__ __forceinline__ uint32_t unit_of(uint32_t table, uint32_t i) { return ((table >> (i * 4)) & 15) * UNIT; }
__device__ __forceinline__ void tma3d(uint32_t dst, const CUtensorMap* m, int c0, int c1, int c2, uint32_t bar) {
  asm volatile("cp.async.bulk.tensor.3d.shared::cluster.global.mbarrier::complete_tx::bytes.L2::cache_hint [%0], [%1, {%3, %4, %5}], [%2], %6;"
               ::"r"(dst), "l"(m), "r"(bar), "r"(c0), "r"(c1), "r"(c2), "l"(l2_stream()) : "memory");
}
template <bool STREAM>
__device__ __forceinline__ void tma3d_mc(uint32_t dst, const CUtensorMap* m, int c0, int c1, int c2, uint32_t bar) {
  if (STREAM)
    asm volatile("cp.async.bulk.tensor.3d.shared::cluster.global.mbarrier::complete_tx::bytes.multicast::cluster.L2::cache_hint [%0], [%1, {%3, %4, %5}], [%2], %6, %7;"
                 ::"r"(dst), "l"(m), "r"(bar), "r"(c0), "r"(c1), "r"(c2), "h"((uint16_t)3), "l"(l2_stream()) : "memory");
  else
    asm volatile("cp.async.bulk.tensor.3d.shared::cluster.global.mbarrier::complete_tx::bytes.multicast::cluster [%0], [%1, {%3, %4, %5}], [%2], %6;"
                 ::"r"(dst), "l"(m), "r"(bar), "r"(c0), "r"(c1), "r"(c2), "h"((uint16_t)3) : "memory");
}
__device__ __forceinline__ void prefetch_map(const CUtensorMap* m) {
  asm volatile("prefetch.tensormap [%0];" ::"l"(m) : "memory");
}
__device__ __forceinline__ void fence_async() { asm volatile("fence.proxy.async.global;" ::: "memory"); }
__device__ __forceinline__ void fence_async_smem() { asm volatile("fence.proxy.async.shared::cta;" ::: "memory"); }
__device__ __forceinline__ void bar_sync(int id, int n) { asm volatile("bar.sync %0, %1;" ::"r"(id), "r"(n) : "memory"); }
__device__ __forceinline__ void bar_arrive(int id, int n) { asm volatile("bar.arrive %0, %1;" ::"r"(id), "r"(n) : "memory"); }
__device__ __forceinline__ void wg_fence() { asm volatile("wgmma.fence.sync.aligned;" ::: "memory"); }
__device__ __forceinline__ void wg_commit() { asm volatile("wgmma.commit_group.sync.aligned;" ::: "memory"); }
template <int N> __device__ __forceinline__ void wg_wait() { asm volatile("wgmma.wait_group.sync.aligned %0;" ::"n"(N) : "memory"); }
__device__ __forceinline__ uint64_t make_desc(uint32_t addr, uint32_t lbo, uint32_t sbo) {
  return (uint64_t)((addr & 0x3FFFF) >> 4) | ((uint64_t)(lbo >> 4) << 16) | ((uint64_t)(sbo >> 4) << 32) | (1ull << 62);
}
__device__ __forceinline__ uint32_t ld_relaxed(const uint32_t* p) {
  uint32_t v; asm volatile("ld.relaxed.gpu.global.u32 %0, [%1];" : "=r"(v) : "l"(p) : "memory"); return v;
}
__device__ __forceinline__ uint32_t ld_acquire(const uint32_t* p) {
  uint32_t v; asm volatile("ld.acquire.gpu.global.u32 %0, [%1];" : "=r"(v) : "l"(p) : "memory"); return v;
}
__device__ __forceinline__ uint4 ld_relaxed4(const uint32_t* p) {
  uint4 v; asm volatile("ld.relaxed.gpu.global.v4.u32 {%0,%1,%2,%3}, [%4];" : "=r"(v.x), "=r"(v.y), "=r"(v.z), "=r"(v.w) : "l"(p) : "memory"); return v;
}
__device__ __forceinline__ uint2 ld_relaxed2(const uint32_t* p) {
  uint2 v; asm volatile("ld.relaxed.gpu.global.v2.u32 {%0,%1}, [%2];" : "=r"(v.x), "=r"(v.y) : "l"(p) : "memory"); return v;
}
__device__ __forceinline__ void st_relaxed(uint32_t* p, uint32_t v) {
  asm volatile("st.relaxed.gpu.global.u32 [%0], %1;" ::"l"(p), "r"(v) : "memory");
}
__device__ __forceinline__ void st_relaxed2(uint32_t* p, uint32_t a, uint32_t b) {
  asm volatile("st.relaxed.gpu.global.v2.u32 [%0], {%1,%2};" ::"l"(p), "r"(a), "r"(b) : "memory");
}
__device__ __forceinline__ void st_relaxed4(uint32_t* p, uint32_t a, uint32_t b, uint32_t c, uint32_t d) {
  asm volatile("st.relaxed.gpu.global.v4.u32 [%0], {%1,%2,%3,%4};" ::"l"(p), "r"(a), "r"(b), "r"(c), "r"(d) : "memory");
}
__device__ __forceinline__ void st_b128(uint32_t* p, uint32_t a, uint32_t b, uint32_t c, uint32_t d) {
  asm volatile("{ .reg .b64 u, v; .reg .b128 w; mov.b64 u, {%1, %2}; mov.b64 v, {%3, %4}; mov.b128 w, {u, v}; st.relaxed.gpu.global.b128 [%0], w; }"
               ::"l"(p), "r"(a), "r"(b), "r"(c), "r"(d) : "memory");
}
__device__ __forceinline__ uint4 ld_b128(const uint32_t* p) {
  uint4 r;
  asm volatile("{ .reg .b64 u, v; .reg .b128 w; ld.relaxed.gpu.global.b128 w, [%4]; mov.b128 {u, v}, w; mov.b64 {%0, %1}, u; mov.b64 {%2, %3}, v; }"
               : "=r"(r.x), "=r"(r.y), "=r"(r.z), "=r"(r.w) : "l"(p) : "memory");
  return r;
}
__device__ __forceinline__ void st_pairs(uint32_t* p, uint32_t a, uint32_t b, uint32_t tag) {
  asm volatile("{ .reg .b64 u, v; mov.b64 u, {%1, %3}; mov.b64 v, {%2, %3}; st.relaxed.gpu.global.v2.b64 [%0], {u, v}; }"
               ::"l"(p), "r"(a), "r"(b), "r"(tag) : "memory");
}
__device__ __forceinline__ uint4 ld_pairs(const uint32_t* p) {
  uint4 v;
  asm volatile("{ .reg .b64 u, v; ld.relaxed.gpu.global.v2.b64 {u, v}, [%4]; mov.b64 {%0, %1}, u; mov.b64 {%2, %3}, v; }"
               : "=r"(v.x), "=r"(v.y), "=r"(v.z), "=r"(v.w) : "l"(p) : "memory");
  return v;
}
__device__ __forceinline__ uint2 ld_pair(const uint32_t* p) {
  uint2 v;
  asm volatile("{ .reg .b64 u; ld.relaxed.gpu.global.b64 u, [%2]; mov.b64 {%0, %1}, u; }" : "=r"(v.x), "=r"(v.y) : "l"(p) : "memory");
  return v;
}
__device__ __forceinline__ void red_release(uint32_t* p, uint32_t v) {
  asm volatile("red.release.gpu.global.add.u32 [%0], %1;" ::"l"(p), "r"(v) : "memory");
}
__device__ __forceinline__ uint32_t ldg_nc1(const void* p) {
  uint32_t v;
  asm volatile("ld.global.nc.u32 %0, [%1];" : "=r"(v) : "l"(p));
  return v;
}
__device__ __forceinline__ uint4 ldg_nc4(const void* p) {
  uint4 v; asm volatile("ld.global.nc.L1::no_allocate.v4.u32 {%0,%1,%2,%3}, [%4];" : "=r"(v.x), "=r"(v.y), "=r"(v.z), "=r"(v.w) : "l"(p)); return v;
}
__device__ __forceinline__ uint4 ldg_stream4(const void* p) {
  uint4 v;
  asm volatile("ld.global.nc.L1::no_allocate.L2::cache_hint.v4.u32 {%0,%1,%2,%3}, [%4], %5;" : "=r"(v.x), "=r"(v.y), "=r"(v.z), "=r"(v.w) : "l"(p), "l"(l2_stream()));
  return v;
}
__device__ __forceinline__ void stg4(void* p, uint4 v) {
  asm volatile("st.global.v4.u32 [%0], {%1,%2,%3,%4};" ::"l"(p), "r"(v.x), "r"(v.y), "r"(v.z), "r"(v.w) : "memory");
}
__device__ __forceinline__ void wait_counter(const uint32_t* p, uint32_t target) {
  uint32_t n = 0;
  while ((int)(ld_acquire(p) - target) < 0) { watchdog(n); }
}
__device__ __forceinline__ uint32_t tagf(float v, uint32_t tag) { return (__float_as_uint(v) & ~3u) | tag; }
__device__ __forceinline__ bool tag_ok(uint4 v, uint32_t tag) { return (((v.x ^ tag) | (v.y ^ tag) | (v.z ^ tag) | (v.w ^ tag)) & 3u) == 0; }
__device__ __forceinline__ float untag_sum(uint32_t a, uint32_t b) { return __uint_as_float(a & ~3u) + __uint_as_float(b & ~3u); }
__device__ __forceinline__ uint4 poll4(const uint32_t* p, uint32_t tag) {
  uint4 v = ld_relaxed4(p);
  uint32_t n = 0;
  while (!tag_ok(v, tag)) { v = ld_relaxed4(p); watchdog(n); }
  return v;
}
__device__ __forceinline__ float bf_lo(uint32_t v) { return __uint_as_float(v << 16); }
__device__ __forceinline__ float bf_hi(uint32_t v) { return __uint_as_float(v & 0xffff0000u); }
__device__ __forceinline__ uint32_t pack_bf(float lo, float hi) {
  uint32_t r; asm("cvt.rn.bf16x2.f32 %0, %1, %2;" : "=r"(r) : "f"(hi), "f"(lo)); return r;
}
__device__ __forceinline__ float rbf(float v) { return __uint_as_float(pack_bf(0.f, v) & 0xffff0000u); }
__device__ __forceinline__ uint32_t hmul2(uint32_t a, uint32_t b) {
  uint32_t r; asm("mul.rn.bf16x2 %0, %1, %2;" : "=r"(r) : "r"(a), "r"(b)); return r;
}
__device__ __forceinline__ uint32_t hadd2(uint32_t a, uint32_t b) {
  uint32_t r; asm("add.rn.bf16x2 %0, %1, %2;" : "=r"(r) : "r"(a), "r"(b)); return r;
}
__device__ __forceinline__ uint32_t hsub2(uint32_t a, uint32_t b) {
  uint32_t r; asm("sub.rn.bf16x2 %0, %1, %2;" : "=r"(r) : "r"(a), "r"(b)); return r;
}
__device__ __forceinline__ uint32_t hmax2(uint32_t a, uint32_t b) {
  uint32_t r; asm("max.bf16x2 %0, %1, %2;" : "=r"(r) : "r"(a), "r"(b)); return r;
}
__device__ __forceinline__ float rcp(float x) { float r; asm("rcp.approx.ftz.f32 %0, %1;" : "=f"(r) : "f"(x)); return r; }
__device__ __forceinline__ float ex2(float x) { float r; asm("ex2.approx.ftz.f32 %0, %1;" : "=f"(r) : "f"(x)); return r; }
__device__ __forceinline__ void stmatrix4(uint32_t addr, uint32_t a, uint32_t b, uint32_t c, uint32_t d) {
  asm volatile("stmatrix.sync.aligned.m8n8.x4.shared.b16 [%0], {%1,%2,%3,%4};" ::"r"(addr), "r"(a), "r"(b), "r"(c), "r"(d) : "memory");
}
__device__ __forceinline__ void ldmatrix4(uint32_t addr, uint32_t& a, uint32_t& b, uint32_t& c, uint32_t& d) {
  asm volatile("ldmatrix.sync.aligned.m8n8.x4.shared.b16 {%0,%1,%2,%3}, [%4];" : "=r"(a), "=r"(b), "=r"(c), "=r"(d) : "r"(addr) : "memory");
}
__device__ __forceinline__ void ldmatrix4t(uint32_t addr, uint32_t& a, uint32_t& b, uint32_t& c, uint32_t& d) {
  asm volatile("ldmatrix.sync.aligned.m8n8.x4.trans.shared.b16 {%0,%1,%2,%3}, [%4];" : "=r"(a), "=r"(b), "=r"(c), "=r"(d) : "r"(addr) : "memory");
}
__device__ __forceinline__ void mma16816(float (&d)[4], uint32_t a0, uint32_t a1, uint32_t a2, uint32_t a3, uint32_t b0, uint32_t b1) {
  asm volatile("mma.sync.aligned.m16n8k16.row.col.f32.bf16.bf16.f32 {%0,%1,%2,%3}, {%4,%5,%6,%7}, {%8,%9}, {%0,%1,%2,%3};"
               : "+f"(d[0]), "+f"(d[1]), "+f"(d[2]), "+f"(d[3]) : "r"(a0), "r"(a1), "r"(a2), "r"(a3), "r"(b0), "r"(b1));
}
__device__ __forceinline__ void sts1(uint32_t a, uint32_t v) { asm volatile("st.shared.u32 [%0], %1;" ::"r"(a), "r"(v) : "memory"); }
__device__ __forceinline__ uint4 lds4(uint32_t a) {
  uint4 v; asm volatile("ld.shared.v4.u32 {%0,%1,%2,%3}, [%4];" : "=r"(v.x), "=r"(v.y), "=r"(v.z), "=r"(v.w) : "r"(a) : "memory"); return v;
}
__device__ __forceinline__ uint2 lds2(uint32_t a) {
  uint2 v; asm volatile("ld.shared.v2.u32 {%0,%1}, [%2];" : "=r"(v.x), "=r"(v.y) : "r"(a) : "memory"); return v;
}
__device__ __forceinline__ uint32_t lds1(uint32_t a) {
  uint32_t v; asm volatile("ld.shared.u32 %0, [%1];" : "=r"(v) : "r"(a) : "memory"); return v;
}
__device__ __forceinline__ void sts2(uint32_t a, uint32_t x, uint32_t y) { asm volatile("st.shared.v2.u32 [%0], {%1,%2};" ::"r"(a), "r"(x), "r"(y) : "memory"); }
__device__ __forceinline__ void sts4(uint32_t a, uint4 v) {
  asm volatile("st.shared.v4.u32 [%0], {%1,%2,%3,%4};" ::"r"(a), "r"(v.x), "r"(v.y), "r"(v.z), "r"(v.w) : "memory");
}
__device__ __forceinline__ float silu_f(float v) { return __fdividef(v, 1.f + __expf(-v)); }
__device__ __forceinline__ uint32_t hfma2(uint32_t a, uint32_t b, uint32_t c) {
  uint32_t r; asm("fma.rn.bf16x2 %0, %1, %2, %3;" : "=r"(r) : "r"(a), "r"(b), "r"(c)); return r;
}
__device__ __forceinline__ void split_inv(float sd, uint32_t& ih, uint32_t& il) {
  const float inv = rcp(sd);
  ih = pack_bf(inv, inv);
  const float lo = inv - bf_lo(ih);
  il = pack_bf(lo, lo);
}
__device__ __forceinline__ uint32_t ln_mod(uint32_t x, uint32_t mean2, uint32_t ih, uint32_t il, uint32_t c1, uint32_t sh) {
  const uint32_t d = hsub2(x, mean2);
  return hadd2(hmul2(hfma2(d, ih, hmul2(d, il)), c1), sh);
}

#define R8(a, i) "+f"(a[i]), "+f"(a[i + 1]), "+f"(a[i + 2]), "+f"(a[i + 3]), "+f"(a[i + 4]), "+f"(a[i + 5]), "+f"(a[i + 6]), "+f"(a[i + 7])
#define D64 "{%0,%1,%2,%3,%4,%5,%6,%7,%8,%9,%10,%11,%12,%13,%14,%15,%16,%17,%18,%19,%20,%21,%22,%23,%24,%25,%26,%27,%28,%29,%30,%31," \
            "%32,%33,%34,%35,%36,%37,%38,%39,%40,%41,%42,%43,%44,%45,%46,%47,%48,%49,%50,%51,%52,%53,%54,%55,%56,%57,%58,%59,%60,%61,%62,%63}"
template <int TB>
__device__ __forceinline__ void mma_ss(float (&d)[64], uint64_t da, uint64_t db, int sc) {
  asm volatile("{\n.reg .pred p;\nsetp.ne.b32 p, %66, 0;\n"
               "wgmma.mma_async.sync.aligned.m64n128k16.f32.bf16.bf16 " D64 ", %64, %65, p, 1, 1, 0, %67;\n}"
               : R8(d, 0), R8(d, 8), R8(d, 16), R8(d, 24), R8(d, 32), R8(d, 40), R8(d, 48), R8(d, 56)
               : "l"(da), "l"(db), "r"(sc), "n"(TB));
}
template <int TB>
__device__ __forceinline__ void mma_rs(float (&d)[64], uint32_t a0, uint32_t a1, uint32_t a2, uint32_t a3, uint64_t db, int sc) {
  asm volatile("{\n.reg .pred p;\nsetp.ne.b32 p, %69, 0;\n"
               "wgmma.mma_async.sync.aligned.m64n128k16.f32.bf16.bf16 " D64 ", {%64,%65,%66,%67}, %68, p, 1, 1, %70;\n}"
               : R8(d, 0), R8(d, 8), R8(d, 16), R8(d, 24), R8(d, 32), R8(d, 40), R8(d, 48), R8(d, 56)
               : "r"(a0), "r"(a1), "r"(a2), "r"(a3), "l"(db), "r"(sc), "n"(TB));
}
#define D128 "{%0,%1,%2,%3,%4,%5,%6,%7,%8,%9,%10,%11,%12,%13,%14,%15,%16,%17,%18,%19,%20,%21,%22,%23,%24,%25,%26,%27,%28,%29,%30,%31," \
             "%32,%33,%34,%35,%36,%37,%38,%39,%40,%41,%42,%43,%44,%45,%46,%47,%48,%49,%50,%51,%52,%53,%54,%55,%56,%57,%58,%59,%60,%61,%62,%63," \
             "%64,%65,%66,%67,%68,%69,%70,%71,%72,%73,%74,%75,%76,%77,%78,%79,%80,%81,%82,%83,%84,%85,%86,%87,%88,%89,%90,%91,%92,%93,%94,%95," \
             "%96,%97,%98,%99,%100,%101,%102,%103,%104,%105,%106,%107,%108,%109,%110,%111,%112,%113,%114,%115,%116,%117,%118,%119,%120,%121,%122,%123,%124,%125,%126,%127}"
#define R128(d, e) R8(d, 0), R8(d, 8), R8(d, 16), R8(d, 24), R8(d, 32), R8(d, 40), R8(d, 48), R8(d, 56), \
                   R8(e, 0), R8(e, 8), R8(e, 16), R8(e, 24), R8(e, 32), R8(e, 40), R8(e, 48), R8(e, 56)
__device__ __forceinline__ void mma256_ss(float (&d)[64], float (&e)[64], uint64_t da, uint64_t db, int sc) {
  asm volatile("{\n.reg .pred p;\nsetp.ne.b32 p, %130, 0;\n"
               "wgmma.mma_async.sync.aligned.m64n256k16.f32.bf16.bf16 " D128 ", %128, %129, p, 1, 1, 0, 1;\n}"
               : R128(d, e) : "l"(da), "l"(db), "r"(sc));
}
__device__ __forceinline__ void mma256_rs(float (&d)[64], float (&e)[64], uint32_t a0, uint32_t a1, uint32_t a2, uint32_t a3, uint64_t db) {
  asm volatile("{\n.reg .pred p;\nsetp.ne.b32 p, 1, 0;\n"
               "wgmma.mma_async.sync.aligned.m64n256k16.f32.bf16.bf16 " D128 ", {%128,%129,%130,%131}, %132, p, 1, 1, 1;\n}"
               : R128(d, e) : "r"(a0), "r"(a1), "r"(a2), "r"(a3), "l"(db));
}
template <int N> __device__ __forceinline__ void keep(float (&a)[N]) {
#pragma unroll
  for (int i = 0; i < N; i++) asm volatile("" : "+f"(a[i])::"memory");
}
template <int N> __device__ __forceinline__ void keep(uint32_t (&a)[N]) {
#pragma unroll
  for (int i = 0; i < N; i++) asm volatile("" : "+r"(a[i])::"memory");
}

#define STAMP(idx) do {} while (0)
#define PROF(grp, cond, idx) do {} while (0)

constexpr float SCL2 = 1.4426950408889634f * 0.08838834764831845f;

__device__ __forceinline__ void pack_p(const float (&s)[64], uint32_t (&p)[32]) {
#pragma unroll
  for (int i = 0; i < 32; i++) p[i] = pack_bf(s[2 * i], s[2 * i + 1]);
}

__device__ __forceinline__ void issue_qk(float (&s)[64], uint32_t q0, uint32_t q1, uint32_t kslot) {
  const uint64_t db = make_desc(kslot, 16, 1024), da0 = make_desc(q0, 16, 1024), da1 = make_desc(q1, 16, 1024);
#pragma unroll
  for (int kk = 0; kk < 8; kk++) mma_ss<0>(s, (kk < 4 ? da0 : da1) + (kk & 3) * 2, db + (kk >> 2) * 1024 + (kk & 3) * 2, kk != 0);
}
__device__ __forceinline__ void issue_pv(float (&o)[64], uint32_t (&p)[32], uint32_t vslot, int acc) {
  uint64_t db = make_desc(vslot, 16384, 1024);
#pragma unroll
  for (int kk = 0; kk < 8; kk++)
    mma_rs<1>(o, p[4 * kk], p[4 * kk + 1], p[4 * kk + 2], p[4 * kk + 3], db + kk * 128, kk == 0 ? acc : 1);
}

template <int H>
__device__ __forceinline__ void store_chunk(const float (&a)[64], uint32_t addr) {
#pragma unroll
  for (int i = 8 * H; i < 8 * H + 8; i += 2)
    stmatrix4(addr ^ ((i & 7) << 4), pack_bf(a[4 * i], a[4 * i + 1]), pack_bf(a[4 * i + 2], a[4 * i + 3]),
              pack_bf(a[4 * i + 4], a[4 * i + 5]), pack_bf(a[4 * i + 6], a[4 * i + 7]));
}
template <int H>
__device__ __forceinline__ void store_chunk(const float (&a)[64], float i0, float i1, uint32_t addr) {
#pragma unroll
  for (int i = 8 * H; i < 8 * H + 8; i += 2)
    stmatrix4(addr ^ ((i & 7) << 4), pack_bf(a[4 * i] * i0, a[4 * i + 1] * i0), pack_bf(a[4 * i + 2] * i1, a[4 * i + 3] * i1),
              pack_bf(a[4 * i + 4] * i0, a[4 * i + 5] * i0), pack_bf(a[4 * i + 6] * i1, a[4 * i + 7] * i1));
}
__device__ __forceinline__ float inv_quad_sum(float l) {
  l += __shfl_xor_sync(0xffffffffu, l, 1);
  l += __shfl_xor_sync(0xffffffffu, l, 2);
  return rcp(l);
}

__device__ __forceinline__ void ln_scalars(float mean, float var, float& mb, float& sd) {
  mb = rbf(mean);
  float r; asm("sqrt.approx.ftz.f32 %0, %1;" : "=f"(r) : "f"(rbf(rbf(var) + 1e-5f)));
  sd = rbf(r);
}

__global__ void __cluster_dims__(2, 1, 1) __launch_bounds__(384, 1) fused_kernel(const __grid_constant__ Maps maps, const Ptrs P) {
  extern __shared__ __align__(1024) uint8_t smem_raw[];
  const uint32_t base = smem_u32(smem_raw);
  const int tid = threadIdx.x, lane = tid & 31;
  const int warp = __shfl_sync(0xffffffffu, tid >> 5, 0);
  const int b = blockIdx.x;
  PROF(31, tid == 0, 0);

  if (b >= NMAIN) {
    float* sc = reinterpret_cast<float*>(smem_raw);
    float* red = sc + DM;
    for (int k = tid; k < DM; k += 384) sc[k] = rbf(silu_f(__bfloat162float(P.c[k])));
    __syncthreads();
    if (tid < 256) {
      const int col = 2048 + (b - NMAIN) * 1024 + (tid & 127) * 8, r0 = (tid >> 7) * 512;
      float acc[8];
#pragma unroll
      for (int e = 0; e < 8; e++) acc[e] = 0.f;
#pragma unroll 1
      for (int r = r0; r < r0 + 512; r += HU) {
        uint4 w[HU];
#pragma unroll
        for (int u = 0; u < HU; u++) w[u] = ldg_stream4(P.w_mod + (size_t)(r + u) * NMOD + col);
#pragma unroll
        for (int u = 0; u < HU; u++) {
          float s = sc[r + u];
          acc[0] += s * bf_lo(w[u].x); acc[1] += s * bf_hi(w[u].x); acc[2] += s * bf_lo(w[u].y); acc[3] += s * bf_hi(w[u].y);
          acc[4] += s * bf_lo(w[u].z); acc[5] += s * bf_hi(w[u].z); acc[6] += s * bf_lo(w[u].w); acc[7] += s * bf_hi(w[u].w);
        }
      }
      if (tid >= 128) {
#pragma unroll
        for (int e = 0; e < 8; e++) red[(tid & 127) * 8 + e] = acc[e];
      }
      const uint32_t tag = ld_relaxed(&g_epoch) % 3 + 1;
      bar_sync(1, 256);
      if (tid < 128) {
        uint32_t o[8];
#pragma unroll
        for (int e = 0; e < 8; e++) o[e] = __float_as_uint(rbf(acc[e] + red[tid * 8 + e])) | tag;
        st_relaxed4(g_mod + col, o[0], o[1], o[2], o[3]);
        st_relaxed4(g_mod + col + 4, o[4], o[5], o[6], o[7]);
        const uint4 wr = ldg_nc4(P.w_r + tid * 8);
        const uint32_t wv[4] = {wr.x, wr.y, wr.z, wr.w};
        float dsum = 0.f;
#pragma unroll
        for (int e = 0; e < 8; e++) {
          const float m = bf_hi(o[e]);
          dsum += (b == NMAIN + 2 ? rbf(1.f + m) : m) * ((e & 1) ? bf_hi(wv[e >> 1]) : bf_lo(wv[e >> 1]));
        }
#pragma unroll
        for (int k = 16; k > 0; k >>= 1) dsum += __shfl_xor_sync(0xffffffffu, dsum, k);
        if (lane == 0) st_relaxed(g_mod + (b - NMAIN) * 4 + warp, tagf(dsum, tag));
      }
    }
    PROF(2, tid == 0, 1);
    return;
  }

  const int rank = b & 1;
  const int rb = ((b >> 4) << 1) | rank, cj = (b >> 1) & 7;
  const uint32_t bfull = base + OFF_BAR, bempty = bfull + NSLOT * 8;
  const uint32_t gfull = bempty + NSLOT * 8, gempty = gfull + 32;
  const uint32_t bar_ofull = gempty + 32;
  const uint32_t bar_ofree = bar_ofull + 16;
  const uint32_t bar_par = bar_ofree + 32;
  const uint32_t bar_mod = bar_par + 8;
  const uint32_t bar_pread = bar_mod + 8;
  const uint32_t bar_xres = bar_pread + 8;
  const uint32_t bar_ring = bar_xres + 8;
  const uint32_t bar_box = bar_ring + 24;
  const uint32_t bar_go = bar_box + 96;
  const uint32_t bar_go2 = bar_go + 16;
  const uint32_t bar_cnt = bar_go + 24;
  const uint32_t xfull = bar_go + 32, xempty = xfull + 32;
  const uint32_t bar_hw = xempty + 32, bar_hx = bar_hw + 8;
  const uint32_t bar_hpub = bar_hx + 16;
  const uint32_t bar_win = bar_hpub + 8;
  const uint32_t bar_rx = bar_win + 8;
  const uint32_t bar_sel = bar_rx + 8;
  const uint32_t bar_gate = bar_sel + 8;
  const uint32_t bar_res = bar_go + 8;
  const uint32_t stage = base + OFF_STAGE, par = base + OFF_PAR;

  if (warp == 8 && elect_one()) {
    for (int s = 0; s < NSLOT; s++) { mbar_init(bfull + s * 8, 1); mbar_init(bempty + s * 8, 16); }
    for (int s = 0; s < 4; s++) { mbar_init(gfull + s * 8, 1); mbar_init(gempty + s * 8, 16); mbar_init(xfull + s * 8, 1); mbar_init(xempty + s * 8, 8); mbar_init(bar_ofree + s * 8, 1); }
    mbar_init(bar_ofull, 128); mbar_init(bar_ofull + 8, 128);
    mbar_init(bar_par, 64); mbar_init(bar_mod, 256); mbar_init(bar_pread, 8); mbar_init(bar_xres, 1);
    mbar_init(bar_ring, 8); mbar_init(bar_ring + 8, 8); mbar_init(bar_ring + 16, 8);
    mbar_init(bar_go, 1); mbar_init(bar_go2, 1); mbar_init(bar_cnt, 1); mbar_init(bar_hpub, 8); mbar_init(bar_res, 1); mbar_init(bar_win, 1); mbar_init(bar_rx, 1); mbar_init(bar_sel, 64); mbar_init(bar_gate, 8);
    for (int s = 0; s < 12; s++) mbar_init(bar_box + s * 8, 1);
    asm volatile("fence.mbarrier_init.release.cluster;" ::: "memory");
    prefetch_map(&maps.x); prefetch_map(&maps.wq); prefetch_map(&maps.k); prefetch_map(&maps.v);
  }
  if (warp == 9 && elect_one()) {
    mbar_init(bar_hw, 1); mbar_init(bar_hx, 1); mbar_init(bar_hx + 8, 1);
    asm volatile("fence.mbarrier_init.release.cluster;" ::: "memory");
    mbar_expect_tx(bar_hw, 32768);
    mbar_expect_tx(bar_hx, 16384);
    mbar_expect_tx(bar_hx + 8, 16384);
    const __nv_bfloat16* xs = P.x + (size_t)(rb * 128 + cj * 16) * DM;
    bulk_load(base + 2 * GST_BYTES, xs, 16384, bar_hx);
    tma2d(stage, &maps.wm, (b >> 1) * 32, rank * 512, bar_hw);
    tma2d(stage + 16384, &maps.wm, (b >> 1) * 32, rank * 512 + 256, bar_hw);
    bulk_load(base + 3 * GST_BYTES, xs + 8 * DM, 16384, bar_hx + 8);
  }
  cluster_arrive();

  if (warp >= 8) {
    asm volatile("setmaxnreg.dec.sync.aligned.u32 40;");
    if (warp < 10) bar_arrive(1, 320);
    const uint32_t epoch = ld_relaxed(&g_epoch);
    cluster_wait();
    if (warp == 8) {
      const int kvrow = (cj >> 1) * SK + (SK - WIN);
      int wch = cj * 8 + rank * 2;
#pragma unroll 1
      for (int ps = 0; ps < 3; ps++) {
        const CUtensorMap* mw = ps == 2 ? &maps.wo : &maps.wq;
        const uint32_t xt = ps == 1 ? XT1 : XT2, wt = ps == 0 ? WT0 : (ps == 1 ? WT1 : WT2);
        const int nst = ps == 2 ? 32 : 16;
        if (ps) {
          mbar_wait(bar_ofree + (ps - 1) * 16, 0);
          fence_async();
        }
#pragma unroll 1
        for (int i = 0; i < nst; i++) {
          const uint32_t bf = gfull + (i & 3) * 8;
          const int kt = ps == 2 ? (((cj & 1) * 4 + ((i >> 1) & 3)) * 4 + (i >> 3)) * 2 + (i & 1) : (i + (ps ? 0 : b & 14)) & 15;
          const uint32_t wd = base + unit_of(wt, i & 3) + rank * UNIT, xd = base + unit_of(xt, i & 3);
          const uint8_t* xs = g_act + (uint32_t)(rb * 80 + (ps - 1) * 16 + kt) * UNIT;
          if (ps == 0 && i == HD) mbar_wait(bar_mod, 0);
          if (ps && i && i < 4) mbar_wait(bempty + (i == 3 ? 3 : i - 1) * 8, 1);
          mbar_wait(gempty + (i & 3) * 8, ((i >> 2) & 1) ^ 1);
          if (elect_one()) {
            mbar_expect_tx(bf, ps ? GST_BYTES : 2 * UNIT);
            tma3d_mc<true>(wd, mw, 0, (i == 31 ? kt ^ (rank * 32) : kt) * 64, i == 31 ? cj * 2 : wch, bf);
          }
          if (ps) {
            if (i == 16) mbar_wait(bar_cnt, 0);
            if (i == 2) mbar_wait(bempty + 16, 1);
            if (elect_one()) {
              if (i == 31) bulk_load(xd, xs, UNIT, bf); else bulk_load_stream(xd, xs, UNIT, bf);
              mbar_arrive_pred(bar_go, i == GOST - 1);
              mbar_arrive_pred(bar_go2, ps * 16 + i == PG0);
              mbar_arrive_pred(bar_res, ((1u << RES0 | 1u << RES1) >> i) & 1);
              if (ps == 2 && b < NFFN && i >= PD0 && i < PD0 + 16)
                asm volatile("cp.async.bulk.prefetch.L2.global [%0], 4096;" ::"l"(P.w_down + (size_t)b * 32768 + (i - PD0) * 2048) : "memory");
            }
          }
        }
        if (ps == 2) break;
        wch = ps ? ((wch >> 3) ^ rank) * 2 : wch + 4;
#pragma unroll 1
        for (int u = 0; u < 16; u++) {
          const bool isk = (u == 0) || ((u & 1) && u < 15);
          const int blk = (isk ? (u + 1) >> 1 : (u == 15 ? 7 : (u >> 1) - 1)) & 3;
          const uint32_t sl = base + unit_of(ps ? AT1 : AT0, u & 3) + rank * UNIT, bf = bfull + (u & 3) * 8;
          if (u < 4) mbar_wait(gempty + ((u + 1) >> 1) * 8, 1);
          mbar_wait(bempty + (u & 3) * 8, ((u >> 2) & 1) ^ 1);
          if (elect_one()) {
            mbar_expect_tx(bf, SLOT_BYTES);
            tma3d_mc<false>(sl, isk ? &maps.k : &maps.v, 0, kvrow + blk * 128, rank, bf);
            if (ps && u >= PF2T && u < PF2T + 2 * PF2 && !((u - PF2T) & 1))
              tma3d_prefetch(&maps.wo, 0, ((((cj & 1) * 4 + (b >> 5)) * 4 + ((u - PF2T) >> 1)) * 2 + ((b >> 4) & 1)) * 64, (cj ^ rank) * 2);
          }
        }
      }
      mbar_wait(bar_ring, 0);
      if (elect_one()) {
        mbar_expect_tx(bar_rx, UNIT);
        bulk_load_stream(base + 8 * UNIT, g_act + (uint32_t)(rb * 80 + 16 + 63 - (cj & 1) * 32) * UNIT, UNIT, bar_rx);
      }
      if (b < NFFN) {
#pragma unroll 1
        for (int u = 0; u < 12; u++) {
          if (u == 2 || u == 8) mbar_wait(bar_ring + 8 + (u & 8), 0);
          if (u >= FPACE) mbar_wait(bar_box + (u - FPACE) * 8, 0);
          const uint32_t dst = base + unit_of(u < 4 ? FT_G : (u < 8 ? FT_U : FT_D), u & 3);
          if (elect_one()) {
            mbar_expect_tx(bar_box + u * 8, UNIT);
            if (u < 8) tma2d(dst, u < 4 ? &maps.wg : &maps.wu, b * 32, (u & 3) * 256, bar_box + u * 8);
            else tma3d(dst, &maps.wd, 0, b * 32, (u - 8) * 4, bar_box + u * 8);
          }
        }
      }
    } else if (warp == 9) {
      const uint32_t target = 8 * (epoch + 1);
#pragma unroll 1
      for (int i = 0; i < 16; i++) {
        if (i == HDX) mbar_wait(bar_mod, 0);
        if (i == NRS) {
          wait_counter(&g_cnt_h[rb * 32], target);
          PROF(1, lane == 0, 26);
          fence_async();
        }
        mbar_wait(xempty + (i & 3) * 8, ((i >> 2) & 1) ^ 1);
        if (elect_one()) {
          mbar_expect_tx(xfull + (i & 3) * 8, UNIT);
          if (i < NRS) tma2d(base + (i & 3) * GST_BYTES, &maps.x, ((2 * cj + i) & 15) * 64, rb * 128, xfull + (i & 3) * 8);
          else bulk_load_stream(base + (i & 3) * GST_BYTES, g_act + (uint32_t)(rb * 80 + ((2 * cj + i) & 15)) * UNIT, UNIT, xfull + (i & 3) * 8);
        }
      }
      prefetch_map(&maps.wo);
#pragma unroll 1
      for (int t = 0; t < 4; t++) {
#pragma unroll 1
        for (int w = 0; w < 2; w++) {
          mbar_wait(bar_ofull + w * 8, t & 1);
          uint8_t* dst = g_act + (uint32_t)(rb * 80 + 16 + (cj * 4 + t) * 2) * UNIT + w * 8192;
          if (elect_one()) {
            bulk_store(dst, base + unit_of(QT, 2 * t) + w * 8192, 8192);
            bulk_store(dst + UNIT, base + unit_of(QT, 2 * t + 1) + w * 8192, 8192);
            asm volatile("cp.async.bulk.commit_group;" ::: "memory");
          }
        }
        if (elect_one()) {
          asm volatile("cp.async.bulk.wait_group.read 0;" ::: "memory");
          mbar_arrive(bar_ofree + t * 8);
          asm volatile("cp.async.bulk.wait_group 0;" ::: "memory");
          fence_async();
          red_release(&g_cnt_o[((rb * 4 + t) * 2 + (cj >> 2)) * 32], 2);
        }
        if (t & 1) {
          wait_counter(&g_cnt_o[(rb * 8 + 2 * t - 2 + (cj & 1)) * 32], target);
          wait_counter(&g_cnt_o[(rb * 8 + 2 * t + (cj & 1)) * 32], target);
        }
      }
      wait_counter(&g_cnt_o[(rb * 8 + 7 - (cj & 1)) * 32], target);
      fence_async();
      if (elect_one()) {
        mbar_arrive(bar_cnt);
        PROF(2, true, 27);
        mbar_expect_tx(bar_xres, 32768);
      }
#pragma unroll 1
      for (int u = 0; u < 2; u++) {
        mbar_wait(bar_res, u);
        if (elect_one()) tma2d(base + OFF_RES + u * UNIT, &maps.x, cj * 128 + u * 64, rb * 128, bar_xres);
      }
      const uint32_t tag = epoch % 3 + 1;
      const uint32_t* inbox = g_cand + (lane & 15);
      mbar_wait(bar_ring + 16, 0);
      uint32_t c0 = ld_relaxed(inbox), n = 0;
#define CAND_STEP(cv)                                                                                        \
      {                                                                                                      \
        const bool valid = (cv & 3u) == tag, all = __all_sync(0xffffffffu, valid);                           \
        const uint32_t best = __reduce_max_sync(0xffffffffu, valid ? cv : 0u);                               \
        const uint32_t blk = __ffs(__ballot_sync(0xffffffffu, cv == best)) - 1;                              \
        if (best) sts2(par + PAR_CONST + 56, best, (blk << 7 | (~best >> 2 & 127)) | (all ? 0x1800 : 0x800)); \
        if (all) break;                                                                                      \
        cv = ld_relaxed(inbox);                                                                              \
      }
      while (true) { CAND_STEP(c0) watchdog(n); }
    } else {
      const int t2 = tid - 320;
      if (t2 == 0) {
        mbar_wait(bar_hpub, 0);
        PROF(1, true, 24);
        red_release(&g_cnt_h[rb * 32], 1);
        PROF(1, true, 25);
        prefetch_map(&maps.wg); prefetch_map(&maps.wu); prefetch_map(&maps.wd); prefetch_map(&maps.out);
      }
      __syncwarp();
      if (b < NFFN) {
        mbar_wait(bar_go2, 0);
        const __nv_bfloat16* pg = ((b & 1) ? P.w_up : P.w_gate) + (b >> 1) * 64 + (size_t)t2 * FF;
        const __nv_bfloat16* pd = P.w_down + (size_t)b * 32768 + t2 * 64;
        PROF(2, t2 == 0, 13);
#pragma unroll 1
        for (int i = 0; i < WN; i += WB) {
          uint32_t v[WB];
#pragma unroll
          for (int u = 0; u < WB; u++)
            asm volatile("ld.global.cg.L2::128B.u32 %0, [%1];" : "=r"(v[u]) : "l"(i < 16 ? pg + (size_t)(i + u) * 64 * FF : pd + (i + u - 16) * 4096));
#pragma unroll
          for (int u = 1; u < WB; u++) v[0] ^= v[u];
          sts1(par + PAR_SINK + t2 * 4, v[0]);
        }
        PROF(2, t2 == 0, 14);
      }
      const uint32_t tag = epoch % 3 + 1;
      mbar_wait(bar_go, 0);
      if (warp == 10) {
        const uint32_t* src = g_mod + 2 * DM + cj * 128 + lane * 4;
        const uint2 wr = *reinterpret_cast<const uint2*>(P.w_r + cj * 128 + lane * 4);
        uint4 vga, vsb, vcb, vgb;
        uint32_t n = 0;
        do {
          vga = ld_relaxed4(src); vsb = ld_relaxed4(src + DM); vcb = ld_relaxed4(src + 2 * DM); vgb = ld_relaxed4(src + 3 * DM);
          watchdog(n);
        } while (!(tag_ok(vga, tag) && tag_ok(vsb, tag) && tag_ok(vcb, tag) && tag_ok(vgb, tag)));
        const float c0 = rbf(1.f + bf_hi(vcb.x)), c1 = rbf(1.f + bf_hi(vcb.y)), c2 = rbf(1.f + bf_hi(vcb.z)), c3 = rbf(1.f + bf_hi(vcb.w));
        const float a0 = c0 * bf_lo(wr.x), a1 = c1 * bf_hi(wr.x), a2 = c2 * bf_lo(wr.y), a3 = c3 * bf_hi(wr.y);
        const uint32_t h0 = pack_bf(a0, a1), h1 = pack_bf(a2, a3);
        const uint32_t t1 = par + PAR_T1 + (lane >> 2) * 64 + (lane & 1) * 32 + (lane & 2) * 2;
        sts1(t1, h0); sts1(t1 + 8, pack_bf(a0 - bf_lo(h0), a1 - bf_hi(h0)));
        sts1(t1 + 16, h1); sts1(t1 + 24, pack_bf(a2 - bf_lo(h1), a3 - bf_hi(h1)));
        sts4(par + PAR_T2 + lane * 32, make_uint4(pack_bf(c0, c1), __byte_perm(vsb.x, vsb.y, 0x7632), __byte_perm(vgb.x, vgb.y, 0x7632), __byte_perm(vga.x, vga.y, 0x7632)));
        sts4(par + PAR_T2 + lane * 32 + 16, make_uint4(pack_bf(c2, c3), __byte_perm(vsb.z, vsb.w, 0x7632), __byte_perm(vgb.z, vgb.w, 0x7632), __byte_perm(vga.z, vga.w, 0x7632)));
      } else if (lane < 4) {
        const uint4 g = poll4(lane < 2 ? g_mod + 5 * DM + b * 8 + lane * 4 : g_mod + 16 - lane * 4, tag);
        sts1(par + PAR_CONST + 60, 0);
        if (lane < 2) sts4(par + PAR_CONST + 16 + lane * 16, g);
        else sts2(par + PAR_CONST + (lane - 2) * 8, __float_as_uint(untag_sum(g.x, g.y) + untag_sum(g.z, g.w)), epoch);
      }
      __syncwarp();
#pragma unroll 4
      for (int q = XR; q < XE; q++) st_b128(g_xch + ((size_t)b * 8 * 256 + q * 64 + t2) * 4, (epoch & 1) << 16, 0, 0, 0);
      for (int q = 0; q < 2; q++) st_relaxed4(g_stats + ((size_t)cj * SEQ + rb * 128 + q * 64 + t2) * 4, 0, 0, 0, 0);
      if (b < NFFN)
        for (int q = 0; q < 4; q++) st_relaxed4(g_ypart + ((size_t)(q * 32 + (t2 >> 1)) * NFFN + b) * 8 + (t2 & 1) * 4, 0, 0, 0, 0);
      st_relaxed4(g_row + rb * 2 * DM + (t2 >> 5) * DM + cj * 128 + (t2 & 31) * 4, 0, 0, 0, 0);
      __threadfence();
      mbar_arrive(bar_par);
      mbar_wait(bar_gate, 0);
      uint32_t have = 0, n = 0;
      while (true) {
        const uint32_t st = lds1(par + PAR_CONST + 60) >> 7;
        if ((st & 31) != have) {
          const uint32_t* hsrc = g_row + (st & 15) * 2 * DM + t2 * 4;
          uint4 hv[4];
          bool ok = true;
#pragma unroll
          for (int i = 0; i < 4; i++) hv[i] = ld_pairs(hsrc + i * 256);
#pragma unroll
          for (int i = 0; i < 4; i++) {
            sts2(base + ((FT_G >> i * 4) & 15) * UNIT + (warp & 1) * 8192 + 256 + lane * 8, hv[i].x, hv[i].z);
            ok = ok && hv[i].y == tag && hv[i].w == tag;
          }
          have = __all_sync(0xffffffffu, ok) ? st & 31 : 0;
        }
        if ((st ^ have) == 32) break;
        watchdog(n);
      }
      mbar_arrive(bar_sel);
    }
    __syncwarp();
    cluster_arrive();
    {
      const uint32_t tag = epoch % 3 + 1, t3 = tid - 256;
      mbar_wait(bar_win, 0);
      uint2 win = lds2(par + PAR_CONST + 56);
      win.y &= 0x7ff;
      const uint32_t* fsrc = g_row + (win.y >> 7) * 2 * DM + (b >> 1) * 16 + (t3 & 3) * 4 + (b & 1) * 2;
      const uint32_t* ysrc = g_ypart + (size_t)b * NFFN * 8 + min(t3, NFFN - 1) * 4;
      uint2 fh = ld_pair(fsrc), fx = ld_pair(fsrc + DM);
      if (PSL) __nanosleep(PSL);
      uint4 ya = ld_relaxed4(ysrc), yb = ld_relaxed4(ysrc + NFFN * 4);
      const float rwin = __uint_as_float(((int)win.x < 0 ? win.x & 0x7fffffffu : ~win.x) & ~0x1ffu);
      const float rs = rbf(rcp(1.f + __expf(-rbf(rwin))));
      uint32_t n = 0;
      while (fh.y != tag || fx.y != tag) { fh = ld_pair(fsrc); fx = ld_pair(fsrc + DM); watchdog(n); }
      while (!(tag_ok(ya, tag) && tag_ok(yb, tag))) {
        if (!tag_ok(ya, tag)) ya = ld_relaxed4(ysrc);
        if (!tag_ok(yb, tag)) yb = ld_relaxed4(ysrc + NFFN * 4);
        watchdog(n);
      }
      __syncwarp();
      PROF(8, t3 == 0, 5);
      float y0 = untag_sum(ya.x, yb.x), y1 = untag_sum(ya.y, yb.y), y2 = untag_sum(ya.z, yb.z), y3 = untag_sum(ya.w, yb.w);
      const bool u1 = lane & 2, u2 = lane & 4;
      y0 = (u1 ? y2 : y0) + __shfl_xor_sync(0xffffffffu, u1 ? y0 : y2, 2);
      y1 = (u1 ? y3 : y1) + __shfl_xor_sync(0xffffffffu, u1 ? y1 : y3, 2);
      y0 = (u2 ? y1 : y0) + __shfl_xor_sync(0xffffffffu, u2 ? y0 : y1, 4);
      y0 += __shfl_xor_sync(0xffffffffu, y0, 8);
      if (!(lane & 8)) sts1(par + PAR_RED + 64 + (t3 >> 4) * 32 + ((lane & 1) * 4 + (lane & 2) + ((lane >> 2) & 1)) * 4, __float_as_uint(y0));
      bar_sync(4, 128);
      if (t3 < 4) {
        y0 = 0.f; y1 = 0.f;
#pragma unroll
        for (int w4 = 0; w4 < 7; w4++) {
          const uint2 v = lds2(par + PAR_RED + 64 + w4 * 32 + t3 * 8);
          y0 += __uint_as_float(v.x); y1 += __uint_as_float(v.y);
        }
        const uint2 gv = lds2(par + PAR_CONST + 16 + t3 * 8);
        const uint32_t upd = hmul2(pack_bf(y0, y1), pack_bf(rs, rs));
        *reinterpret_cast<uint32_t*>(P.out + (size_t)win.y * DM + b * 8 + t3 * 2) =
            hadd2(fx.x, hmul2(__byte_perm(gv.x, gv.y, 0x7632), hadd2(fh.x, upd)));
        if (b == 0 && t3 == 0) st_relaxed(&g_epoch, epoch + 1);
      }
      PROF(31, t3 == 0, 36);
    }
    cluster_wait();
  } else {
    const int wg = warp >> 2;

    uint32_t tag;
    {
      uint32_t* const pmod = g_modp + rank * 2 * DM + (b >> 1) * 32 + lane;
      uint32_t* const pln = g_ln1 + (rb * 128 + cj * 16 + warp) * 4;
      const uint32_t cv = ldg_nc1(P.c + rank * 512 + tid * 2);
      const uint32_t epoch = ld_relaxed(&g_epoch);
      if (warp == 0) st_relaxed(pmod, 0);
      if (lane == 0) { st_relaxed2(pln, 0, 0); st_relaxed2(pln + 32, 0, 0); }
      asm volatile("setmaxnreg.inc.sync.aligned.u32 232;");
      sts1(par + tid * 4, pack_bf(silu_f(bf_lo(cv)), silu_f(bf_hi(cv))));
      bar_sync(1, 320);
      tag = epoch % 3 + 1;
#pragma unroll
      for (int part = 0; part < 3; part++) {
        if (part != 1) {
          const uint32_t xa = base + (2 + part / 2) * GST_BYTES + warp * 2048 + lane * 16;
          mbar_wait(bar_hx + part * 4, 0);
          float s0 = 0.f, s1 = 0.f, q0 = 0.f, q1 = 0.f;
#pragma unroll
          for (int q = 0; q < 4; q++) {
            const uint4 xv = lds4(xa + q * 512);
            const uint32_t u[4] = {xv.x, xv.y, xv.z, xv.w};
#pragma unroll
            for (int e = 0; e < 4; e++) { const float lo = bf_lo(u[e]), hi = bf_hi(u[e]); s0 += lo; s1 += hi; q0 += lo * lo; q1 += hi * hi; }
          }
          s0 += s1; q0 += q1;
#pragma unroll
          for (int o = 16; o > 0; o >>= 1) { s0 += __shfl_xor_sync(0xffffffffu, s0, o); q0 += __shfl_xor_sync(0xffffffffu, q0, o); }
          const float mean = s0 * (1.f / DM);
          float mb, sd;
          ln_scalars(mean, fmaxf(q0 * (1.f / DM) - mean * mean, 0.f), mb, sd);
          if (lane == 0) st_relaxed2(pln + part * 16, __float_as_uint(mb) | tag, __float_as_uint(sd) | tag);
          PROF(1, tid == 0 && part == 2, 4);
        } else {
          float acc[8];
#pragma unroll
          for (int e = 0; e < 8; e++) acc[e] = 0.f;
          const uint32_t wa = stage + (tid >> 2) * 64 + (((tid ^ (tid >> 3)) & 3) << 4), sa = par + (tid >> 3) * 4, sh = (tid & 4) ? 0x3244 : 0x1044;
          mbar_wait(bar_hw, 0);
#pragma unroll
          for (int p = 0; p < 8; p++) {
            const uint4 w = lds4(wa + p * 4096);
            const float s = __uint_as_float(__byte_perm(lds1(sa + p * 128), 0, sh));
            acc[0] += s * bf_lo(w.x); acc[1] += s * bf_hi(w.x); acc[2] += s * bf_lo(w.y); acc[3] += s * bf_hi(w.y);
            acc[4] += s * bf_lo(w.z); acc[5] += s * bf_hi(w.z); acc[6] += s * bf_lo(w.w); acc[7] += s * bf_hi(w.w);
          }
#pragma unroll
          for (int e = 0; e < 4; e++) {
            const bool up = lane & 16;
            acc[e] = (up ? acc[e + 4] : acc[e]) + __shfl_xor_sync(0xffffffffu, up ? acc[e] : acc[e + 4], 16);
          }
#pragma unroll
          for (int e = 0; e < 2; e++) {
            const bool up = lane & 8;
            acc[e] = (up ? acc[e + 2] : acc[e]) + __shfl_xor_sync(0xffffffffu, up ? acc[e] : acc[e + 2], 8);
          }
          {
            const bool up = lane & 4;
            acc[0] = (up ? acc[1] : acc[0]) + __shfl_xor_sync(0xffffffffu, up ? acc[0] : acc[1], 4);
          }
          sts1(par + 1024 + warp * 128 + ((lane & 3) * 8 + (lane >> 2)) * 4, __float_as_uint(acc[0]));
          bar_sync(1, 256);
          if (warp == 0) {
            float s = 0.f;
#pragma unroll
            for (int w8 = 0; w8 < 8; w8++) s += __uint_as_float(lds1(par + 1024 + w8 * 128 + lane * 4));
            st_relaxed(pmod, (__float_as_uint(s) & ~3u) | tag);
          }
          PROF(1, tid == 0, 3);
        }
      }
      {
        uint2 s0 = ld_relaxed2(g_ln1 + (rb * 128 + (tid & 127)) * 4);
        uint4 v[4];
#pragma unroll
        for (int q = 0; q < 4; q++) v[q] = ld_relaxed4(g_modp + q * DM + tid * 4);
        {
          uint32_t n = 0;
          while (!(tag_ok(v[0], tag) && tag_ok(v[1], tag) && tag_ok(v[2], tag) && tag_ok(v[3], tag))) {
#pragma unroll
            for (int q = 0; q < 4; q++)
              if (!tag_ok(v[q], tag)) v[q] = ld_relaxed4(g_modp + q * DM + tid * 4);
            if (((s0.x ^ tag) | (s0.y ^ tag)) & 3u) s0 = ld_relaxed2(g_ln1 + (rb * 128 + (tid & 127)) * 4);
            watchdog(n);
          }
        }
        const uint32_t d = stage + (tid >> 2) * 64 + (tid & 1) * 32 + (tid & 2) * 2;
        sts1(d, pack_bf(1.f + rbf(untag_sum(v[1].x, v[3].x)), 1.f + rbf(untag_sum(v[1].y, v[3].y))));
        sts1(d + 16, pack_bf(1.f + rbf(untag_sum(v[1].z, v[3].z)), 1.f + rbf(untag_sum(v[1].w, v[3].w))));
        sts1(d + 8, pack_bf(untag_sum(v[0].x, v[2].x), untag_sum(v[0].y, v[2].y)));
        sts1(d + 24, pack_bf(untag_sum(v[0].z, v[2].z), untag_sum(v[0].w, v[2].w)));
        if (wg == 0) {
          uint32_t n = 0;
          while (((s0.x ^ tag) | (s0.y ^ tag)) & 3u) { s0 = ld_relaxed2(g_ln1 + (rb * 128 + tid) * 4); watchdog(n); }
          uint32_t ih, il;
          split_inv(bf_hi(s0.y), ih, il);
          sts4(stage + 4096 + tid * 16, make_uint4(__byte_perm(s0.x, 0, 0x3232), ih, il, 0));
        }
        mbar_arrive(bar_mod);
      }
      cluster_wait();
      if (wg == 1) bar_arrive(2, 256);
      mbar_wait(bar_mod, 0);
      PROF(1, tid == 0, 2);
    }

    float f0 = 0.f, f1 = 0.f;
    const uint32_t rempty = lane < 2 ? mapa(bempty, lane & 1) : 0;
    constexpr uint32_t GE = NSLOT * 8 + 32;
    float o[64], s[64];
#pragma unroll 1
    for (int ps = 0; ps < 3; ps++) {
      {
        const uint32_t xt = ps == 1 ? XT1 : XT2, wt = ps == 1 ? WT1 : WT2;
        const int nst = ps == 2 ? 28 : 14;
        if (ps == 0) {
          float ga[64], gb[64];
#pragma unroll
          for (int i = 0; i < 64; i++) { ga[i] = 0.f; gb[i] = 0.f; }
          uint32_t a[2][16];
          const uint32_t l = fresh_lane();
          const uint4 r0 = lds4(stage + 4096 + (warp * 16 + (l >> 2)) * 16), r1 = lds4(stage + 4096 + 128 + (warp * 16 + (l >> 2)) * 16);
          auto transform = [&](int i, uint32_t (&f)[16], uint32_t z) {
            const uint32_t ad = base + (i & 3) * GST_BYTES + wg * 8192 + frag_offset(warp) + z;
            mbar_wait(xfull + (i & 3) * 8, i >> 2);
#pragma unroll
            for (int kk = 0; kk < 4; kk++) ldmatrix4(ad ^ (kk * 32), f[4 * kk], f[4 * kk + 1], f[4 * kk + 2], f[4 * kk + 3]);
#pragma unroll
            for (int kk = 0; kk < 4; kk++) {
              const uint4 m = lds4(stage + (l & 3) * 16 + ((2 * cj + i) & 15) * 256 + kk * 64);
              f[4 * kk] = ln_mod(f[4 * kk], r0.x, r0.y, r0.z, m.x, m.z);
              f[4 * kk + 1] = ln_mod(f[4 * kk + 1], r1.x, r1.y, r1.z, m.x, m.z);
              f[4 * kk + 2] = ln_mod(f[4 * kk + 2], r0.x, r0.y, r0.z, m.y, m.w);
              f[4 * kk + 3] = ln_mod(f[4 * kk + 3], r1.x, r1.y, r1.z, m.y, m.w);
            }
            keep(f);
            mbar_arrive_pred(xempty + (i & 3) * 8, l == 0);
          };
          auto publish = [&](int u, uint32_t (&f)[16]) {
            const uint32_t sc = stage + 8192 + wg * 8192;
#pragma unroll
            for (int kk = 0; kk < 4; kk++) stmatrix4((sc + frag_offset(warp)) ^ (kk * 32), f[4 * kk], f[4 * kk + 1], f[4 * kk + 2], f[4 * kk + 3]);
            __syncwarp();
            const uint32_t src = sc + (warp & 3) * 2048 + l * 16;
            uint8_t* dst = g_act + (uint32_t)(rb * 80 + cj * 2 + u) * UNIT + warp * 2048 + l * 16;
#pragma unroll
            for (int p4 = 0; p4 < 4; p4++) stg4(dst + p4 * 512, lds4(src + p4 * 512));
            __syncwarp();
            if (u == 1) mbar_arrive_pred(bar_hpub, l == 0);
          };
          auto multiply = [&](int i, uint32_t (&f)[16]) {
            mbar_wait(gfull + (i & 3) * 8, i >> 2);
            const uint64_t db = make_desc(base + (i & 3) * GST_BYTES + UNIT, 8192, 1024);
            wg_fence();
#pragma unroll
            for (int kk = 0; kk < 4; kk++) mma256_rs(ga, gb, f[4 * kk], f[4 * kk + 1], f[4 * kk + 2], f[4 * kk + 3], db + kk * 128);
            wg_commit();
          };
          transform(0, a[0], 0); publish(0, a[0]); transform(1, a[1], 0); multiply(0, a[0]); publish(1, a[1]);
#pragma unroll
          for (int i = 1; i < NRS; i++) {
            if (i >= 2) {
              uint32_t z = r0.w;
#pragma unroll
              for (int k = 0; k < 16; k += 2) asm volatile("lop3.b32 %0, %1, %2, %0, 0xA8;" : "+r"(z) : "r"(a[i & 1][k]), "r"(a[i & 1][k + 1]));
              transform(i, a[i & 1], z);
            }
            multiply(i, a[i & 1]);
            wg_wait<1>();
            mbar_arrive_cl(rempty, GE + ((i + 3) & 3) * 8);
          }
          mbar_arrive_pred(bar_pread, l == 0);
#pragma unroll 1
          for (int i = NRS; i < 14; i++) {
            mbar_wait(xfull + (i & 3) * 8, (i >> 2) & 1);
            mbar_wait(gfull + (i & 3) * 8, (i >> 2) & 1);
            const uint32_t xa = base + (i & 3) * GST_BYTES;
            const uint64_t da = make_desc(xa + wg * 8192, 16, 1024), db = make_desc(xa + UNIT, 8192, 1024);
            if (i == 13) bar_sync(2 + wg, 256);
            wg_fence();
#pragma unroll
            for (int kk = 0; kk < 4; kk++) mma256_ss(ga, gb, da + kk * 2, db + kk * 128, 1);
            wg_commit();
            if (i == 13) bar_arrive(3 - wg, 256);
            wg_wait<1>();
            uint32_t z = r0.w;
#pragma unroll
            for (int k = 0; k < 16; k += 2) asm volatile("lop3.b32 %0, %1, %2, %0, 0xA8;" : "+r"(z) : "r"(a[1][k]), "r"(a[1][k + 1]));
            mbar_arrive_cl(rempty, GE + ((i + 3) & 3) * 8 + z);
            mbar_arrive_pred(xempty + ((i + 3) & 3) * 8, l == 0 && i != NRS);
          }
          mbar_wait(xfull + 16, 1);
          mbar_wait(xfull + 24, 1);
          wg_wait<0>();
          keep(ga); keep(gb);
#pragma unroll
          for (int i = 0; i < 64; i++) {
            asm volatile("mov.b32 %0, %1;" : "=f"(s[i]) : "f"(ga[i]));
            asm volatile("mov.b32 %0, %1;" : "=f"(o[i]) : "f"(gb[i]));
          }
        } else {
          float ga[64], gb[64];
#pragma unroll
          for (int i = 0; i < 64; i++) {
            asm volatile("mov.b32 %0, %1;" : "=f"(ga[i]) : "f"(s[i]));
            asm volatile("mov.b32 %0, %1;" : "=f"(gb[i]) : "f"(o[i]));
          }
#pragma unroll 1
          for (int i = 0; i < nst; i++) {
            mbar_wait(gfull + (i & 3) * 8, (i >> 2) & 1);
            const uint64_t da = make_desc(base + unit_of(xt, i & 3) + wg * 8192, 16, 1024), db = make_desc(base + unit_of(wt, i & 3), 8192, 1024);
            if (i == nst - 1) bar_sync(2 + wg, 256);
            wg_fence();
#pragma unroll
            for (int kk = 0; kk < 4; kk++) mma256_ss(ga, gb, da + kk * 2, db + kk * 128, kk ? 1 : i);
            wg_commit();
            if (i == nst - 1) bar_arrive(3 - wg, 256);
            wg_wait<1>();
            mbar_arrive_cl(rempty, GE + ((i + 3) & 3) * 8, i != 0);
            PROF(4, tid == 0 && (i & 3) == 0, 40 + (ps - 1) * 4 + i / 4);
          }
          wg_wait<0>();
          keep(ga); keep(gb);
#pragma unroll
          for (int i = 0; i < 64; i++) {
            asm volatile("mov.b32 %0, %1;" : "=f"(s[i]) : "f"(ga[i]));
            asm volatile("mov.b32 %0, %1;" : "=f"(o[i]) : "f"(gb[i]));
          }
        }
        mbar_arrive_cl(rempty, GE + (ps == 2 ? 24 : 8));
        if (ps == 2) break;
      }
      const uint32_t qw = base + wg * 8192, qt = QT >> (16 * ps), at = ps ? AT1 : AT0;
      {
        const uint32_t wt = ps ? WT1 : WT0;
        const uint64_t da0 = make_desc(qw + unit_of(qt, 2), 16, 1024), da1 = make_desc(qw + unit_of(qt, 3), 16, 1024);
        const uint64_t db0 = make_desc(base + unit_of(wt, 2), 8192, 1024), db1 = make_desc(base + unit_of(wt, 3), 8192, 1024);
        mbar_wait(gfull + 16, 1);
        mbar_wait(gfull + 24, 1);
        bar_sync(2 + wg, 256);
        wg_fence();
#pragma unroll
        for (int kk = 0; kk < 8; kk++) mma_ss<1>(s, (kk < 4 ? da0 : da1) + (kk & 3) * 2, (kk < 4 ? db0 : db1) + (kk & 3) * 128, 1);
        wg_commit();
        bar_arrive(3 - wg, 256);
        mbar_wait(ps == 0 ? bar_pread : bar_ofree + 8, 0);
        mbar_wait(bfull, 0);
        wg_wait<0>();
        keep(s);
        PROF(2, tid == 0, 8 + ps * 8);
        store_chunk<0>(s, qw + unit_of(qt, 0) + frag_offset(warp));
        store_chunk<1>(s, qw + unit_of(qt, 1) + frag_offset(warp));
        fence_async_smem();
        bar_sync(2 + wg, 256);
        wg_fence();
        issue_qk(s, qw + unit_of(qt, 0), qw + unit_of(qt, 1), base + unit_of(at, 0));
        wg_commit();
#pragma unroll
        for (int kk = 0; kk < 8; kk++) mma_ss<1>(o, (kk < 4 ? da0 : da1) + (kk & 3) * 2, (kk < 4 ? db0 : db1) + UNIT / 16 + (kk & 3) * 128, 1);
        wg_commit();
        bar_arrive(3 - wg, 256);
        wg_wait<1>();
        keep(s);
        mbar_arrive_cl(rempty, 0);
      }
      PROF(4, tid == 0 && ps == 1, 61);
      float l0 = 0.25f, l1 = 0.25f;
      auto step = [&](auto odd_c, const int j, uint32_t (&pw)[32], uint32_t (&pr)[32]) {
        constexpr bool ODD = decltype(odd_c)::value;
        const bool first = !ODD && (j & 2) == 0, last = ODD && j == 7;
        const uint32_t ph = (j >> 1) & 1;
        float i0, i1, a0, a1;
        if (first) { i0 = inv_quad_sum(l0); i1 = inv_quad_sum(l1); l0 = 0.f; l1 = 0.f; }
        bool redo = !ODD && (j | ps) == 0, again = false;
        while (true) {
          if (redo) {
            float m0 = fmaxf(s[0], s[1]), m1 = fmaxf(s[2], s[3]);
#pragma unroll
            for (int i = 1; i < 16; i++) { m0 = fmaxf(m0, fmaxf(s[4 * i], s[4 * i + 1])); m1 = fmaxf(m1, fmaxf(s[4 * i + 2], s[4 * i + 3])); }
            m0 = fmaxf(m0, __shfl_xor_sync(0xffffffffu, m0, 1)); m1 = fmaxf(m1, __shfl_xor_sync(0xffffffffu, m1, 1));
            m0 = fmaxf(m0, __shfl_xor_sync(0xffffffffu, m0, 2)); m1 = fmaxf(m1, __shfl_xor_sync(0xffffffffu, m1, 2));
            m0 *= SCL2; m1 *= SCL2;
            if (!first) {
              m0 = fmaxf(m0, f0); m1 = fmaxf(m1, f1);
              const float c0 = ex2(f0 - m0), c1 = ex2(f1 - m1);
              l0 *= c0; l1 *= c1;
              wg_wait<0>();
              keep(o);
#pragma unroll
              for (int i = 0; i < 16; i++) { o[4 * i] *= c0; o[4 * i + 1] *= c0; o[4 * i + 2] *= c1; o[4 * i + 3] *= c1; }
            }
            f0 = m0; f1 = m1;
          }
          float b0 = 0.f, b1 = 0.f;
          a0 = 0.f; a1 = 0.f;
#pragma unroll
          for (int i = 0; i < 16; i++) {
            const float e0 = ex2(fmaf(s[4 * i], SCL2, -f0)), e1 = ex2(fmaf(s[4 * i + 1], SCL2, -f0));
            const float e2 = ex2(fmaf(s[4 * i + 2], SCL2, -f1)), e3 = ex2(fmaf(s[4 * i + 3], SCL2, -f1));
            a0 += e0; b0 += e1; a1 += e2; b1 += e3;
            pw[2 * i] = pack_bf(e0, e1); pw[2 * i + 1] = pack_bf(e2, e3);
            if (i == VREL) {
#pragma unroll
              for (int k = 0; k < 2 * VREL + 2; k++) asm volatile("" : "+r"(pw[k])::"memory");
              mbar_wait(bfull + (ODD ? 24 : 8), ph);
              wg_wait<0>();
              mbar_arrive_cl(rempty, ODD ? 16 : (j ? 0 : GE + 16), !again);
              if (!ODD) mbar_arrive_cl(rempty, GE + 24, !again && j == 0);
#pragma unroll
              for (int k = 4 * VREL + 4; k < 64; k++) asm volatile("" : "+f"(s[k])::"memory");
            }
          }
          a0 += b0; a1 += b1;
          if (redo) break;
          redo = __any_sync(0xffffffffu, !(a0 + a1 < 0x1p70f));
          if (first) {
            uint32_t m0 = __ballot_sync(0xffffffffu, a0 > 0x1p-50f), m1 = __ballot_sync(0xffffffffu, a1 > 0x1p-50f);
            m0 |= m0 >> 1; m1 |= m1 >> 1; m0 |= m0 >> 2; m1 |= m1 >> 2;
            redo = redo || (m0 & m1 & 0x11111111u) != 0x11111111u;
          }
          if (!redo) break;
          again = true;
        }
        l0 += a0; l1 += a1;
        keep(pw);
        keep(o);
        const uint32_t qo = qt >> (j ? 0 : 8);
        if (first) store_chunk<0>(o, i0, i1, qw + unit_of(qo, 0) + frag_offset(warp));
        keep(o);
        bar_sync(2 + wg, 256);
        if (!last) {
          const uint32_t qn = qt >> (j >= 3 ? 8 : 0);
          wg_fence();
          issue_qk(s, qw + unit_of(qn, 0), qw + unit_of(qn, 1), base + unit_of(at, ODD ? 3 : 1));
          wg_commit();
          mbar_wait(bfull + (ODD ? 0 : 16), ODD ? ph ^ 1 : ph);
        }
        if (first) { store_chunk<1>(o, i0, i1, qw + unit_of(qo, 1) + frag_offset(warp)); keep(o); }
        wg_fence();
        issue_pv(o, pw, base + unit_of(at, ODD ? (last ? 3 : 0) : 2), !first);
        wg_commit();
        bar_arrive(3 - wg, 256);
        if (first) { fence_async_smem(); mbar_arrive_pred(bar_ofull + wg * 8, j); PROF(2, tid == 0 && j, 9 + ps * 8); }
        wg_wait<1>();
        keep(s);
        mbar_arrive_cl(rempty, ODD ? 24 : 8, !last);
        PROF(4, tid == 0 && ps == 1, 51 + j);
      };
      uint32_t pa[32], pb[32];
#pragma unroll 1
      for (int j = 0; j < 8; j += 2) {
        step(std::false_type{}, j, pa, pb);
        step(std::true_type{}, j + 1, pb, pa);
      }
      {
        const float i0 = inv_quad_sum(l0), i1 = inv_quad_sum(l1);
        wg_wait<0>();
        keep(o);
        mbar_arrive_cl(rempty, 24);
        store_chunk<0>(o, i0, i1, qw + unit_of(qt, 2) + frag_offset(warp));
        store_chunk<1>(o, i0, i1, qw + unit_of(qt, 3) + frag_offset(warp));
        fence_async_smem();
        mbar_arrive(bar_ofull + wg * 8);
      }
      PROF(2, tid == 0, 10 + ps * 8);
    }

    const int ln = fresh_lane(), g = ln >> 2, tq = ln & 3, ct = warp * 32 + ln;
    const bool lane0 = ln == 0;
    const int lrow0 = warp * 16 + g;
    const int grow0 = rb * 128 + lrow0;
    const uint32_t res = base + OFF_RES, trow = res + wg * 8192 + frag_offset(warp);
    uint32_t xr[32];
    uint4 sv[4], own;
    uint32_t* sp[4];
#pragma unroll
    for (int k = 0; k < 4; k++) sp[k] = g_stats + ((((tq >> 1) * 4 + k) ^ cj) * SEQ + grow0 + (tq & 1) * 8) * 4;
    {
      const uint64_t da = make_desc(base + wg * 8192, 16, 1024), db = make_desc(base, 8192, 1024);
      constexpr int U = UNIT / 16;
#define HALF_STAGE(acc, xu, wu) _Pragma("unroll") for (int kk = 0; kk < 4; kk++) mma_ss<1>(acc, da + (xu) * U + kk * 2, db + (wu) * U + kk * 128, 1)
      PROF(10, ct == PT, 19); STAMP(0);
      cluster_arrive();
      mbar_wait(gfull, 1);
      mbar_wait(gfull + 8, 1);
      bar_sync(2 + wg, 256);
      wg_fence();
      HALF_STAGE(o, 6, 8);
      HALF_STAGE(o, 9, 11);
      wg_commit();
      STAMP(16);
      mbar_wait(gfull + 16, 1);
      STAMP(17);
      wg_fence();
      HALF_STAGE(o, 12, 1);
      wg_commit();
      bar_arrive(3 - wg, 256);
      mbar_wait(bar_par, 0);
      uint32_t* xo = g_xch + ((size_t)b * 8 * 256 + ct) * 4;
      const uint32_t* xi = g_xch + ((size_t)(b ^ 2) * 8 * 256 + ct) * 4;
      const uint32_t par1 = (~lds1(par + PAR_CONST + 4) & 1) << 16;
      wg_wait<0>();
      keep(o);
      mbar_arrive_pred(bar_ring, lane0);
      PROF(8, ct == PT, 20); STAMP(1);
#define SEND(i) st_b128(xo + (i) * 1024, (pack_bf(o[8 * (i)], o[8 * (i) + 1]) & ~0x10000u) | par1, pack_bf(o[8 * (i) + 2], o[8 * (i) + 3]), \
                        pack_bf(o[8 * (i) + 4], o[8 * (i) + 5]), pack_bf(o[8 * (i) + 6], o[8 * (i) + 7]))
#pragma unroll
      for (int i = 0; i < NS1; i++) SEND(i);
      PROF(8, ct == PT, 21); STAMP(2);
      bar_sync(2 + wg, 256);
      wg_fence();
      HALF_STAGE(s, 6, 7);
      HALF_STAGE(s, 9, 10);
      HALF_STAGE(s, 12, 0);
      wg_commit();
      bar_arrive(3 - wg, 256);
      STAMP(18);
      mbar_wait(gfull + 24, 1);
#pragma unroll
      for (int i = NS1; i < 8; i++) SEND(i);
      uint4 v[8];
#pragma unroll
      for (int i = 0; i < 4; i++) v[i] = ld_b128(xi + i * 1024);
      STAMP(19);
      mbar_wait(bar_rx, 0);
      wg_wait<0>();
      mbar_arrive_pred(bar_ring + 8, lane0);
      bar_sync(2 + wg, 256);
      STAMP(20);
#pragma unroll
      for (int i = 4; i < 8; i++) v[i] = ld_b128(xi + i * 1024);
      mbar_wait(bar_xres, 0);
      wg_fence();
      HALF_STAGE(s, 13, 2);
      HALF_STAGE(s, 8, 3);
      wg_commit();
      bar_arrive(3 - wg, 256);
      STAMP(21);
      uint32_t ga[16];
      uint4 bw[8];
#pragma unroll
      for (int i = 0; i < 8; i++) {
        ga[2 * i] = lds1(par + PAR_T2 + i * 128 + tq * 16 + 12); ga[2 * i + 1] = lds1(par + PAR_T2 + i * 128 + 64 + tq * 16 + 12);
        bw[i] = lds4(par + PAR_T1 + i * 64 + tq * 16);
        if (!(g & 1)) { bw[i].x = 0x3f803f80u; bw[i].y = 0x3f803f80u; }
      }
      mbar_wait(bar_xres, 0);
      wg_wait<0>();
      keep(s);
      mbar_arrive_pred(bar_ring + 16, lane0);
      PROF(10, ct == PT, 23); STAMP(4);
#pragma unroll
      for (int i = 0; i < 16; i += 2) ldmatrix4((trow ^ ((i & 7) << 4)) + (i >> 3) * 16384, xr[2 * i], xr[2 * i + 1], xr[2 * i + 2], xr[2 * i + 3]);
#pragma unroll
      for (int k = 0; k < 4; k++) sv[k] = ld_b128(sp[k]);
      uint32_t pk[32];
      pack_p(s, pk);
      keep(pk);
      {
        uint32_t n = 0;
        bool ok;
        do {
          ok = true;
#pragma unroll
          for (int i = 0; i < 8; i++)
            if ((v[i].x & 0x10000u) != par1) { v[i] = ld_b128(xi + i * 1024); ok = false; }
          watchdog(n);
        } while (!ok);
      }
      __syncwarp();
      PROF(8, ct == PT, 22); STAMP(3);
      float ds[4] = {0.f, 0.f, 0.f, 0.f}, dl[4] = {0.f, 0.f, 0.f, 0.f}, q0[4] = {0.f, 0.f, 0.f, 0.f}, q1[4] = {0.f, 0.f, 0.f, 0.f};
#pragma unroll
      for (int i = 0; i < 8; i++) {
        const uint32_t u0 = hfma2(ga[2 * i], hadd2(pk[4 * i], v[i].x & ~0x10000u), xr[4 * i]);
        const uint32_t u1 = hfma2(ga[2 * i], hadd2(pk[4 * i + 1], v[i].y), xr[4 * i + 1]);
        const uint32_t u2 = hfma2(ga[2 * i + 1], hadd2(pk[4 * i + 2], v[i].z), xr[4 * i + 2]);
        const uint32_t u3 = hfma2(ga[2 * i + 1], hadd2(pk[4 * i + 3], v[i].w), xr[4 * i + 3]);
        xr[4 * i] = u0; xr[4 * i + 1] = u1; xr[4 * i + 2] = u2; xr[4 * i + 3] = u3;
        mma16816(ds, u0, u1, u2, u3, bw[i].x, bw[i].y);
        mma16816(dl, u0, u1, u2, u3, bw[i].z, bw[i].w);
        mma16816(q0, u0, u1, u2, u3, u0, u2);
        mma16816(q1, u0, u1, u2, u3, u1, u3);
      }
      const float sqa = __shfl_sync(0xffffffffu, (g & 1) ? q0[1] : q0[0], g * 4 + (g >> 1));
      const float sqb = __shfl_sync(0xffffffffu, (g & 1) ? q1[3] : q1[2], g * 4 + (g >> 1));
      own = (tq & 1) ? make_uint4(__float_as_uint(ds[2]), __float_as_uint(sqb), __float_as_uint(ds[3] + dl[3]), tag)
                                 : make_uint4(__float_as_uint(ds[0]), __float_as_uint(sqa), __float_as_uint(ds[1] + dl[1]), tag);
      if (tq < 2) st_b128(sp[0], own.x, own.y, own.z, own.w);
    }
    PROF(8, ct == PT, 29); STAMP(5);
    uint32_t mm, ih, il;
    float rbest;
    uint32_t wf[128];
    const uint32_t frow = (ln & 7) + (ln >> 4) * 8;
    const uint32_t wfo = base + (warp & 1) * 8192 + frow * 64 + ((((ln >> 3) & 1) ^ ((frow >> 1) & 3)) << 4);
#define LOAD_WF(m) _Pragma("unroll") for (int f = 0; f < 16; f++) {                                                   \
      const int r = ((f >> 1) * 4 + (m) * 2 + (f & 1)) * 4;                                                           \
      ldmatrix4t(((wfo + unit_of((m) ? FT_U : FT_G, warp >> 1)) ^ ((f & 1) * 32)) + (f >> 1) * 1024, wf[r], wf[r + 1], wf[r + 2], wf[r + 3]); \
    }
    bool early, wait1;
    {
#pragma unroll
      for (int i = 0; i < 16; i += 2) stmatrix4((trow ^ ((i & 7) << 4)) + (i >> 3) * 16384, xr[2 * i], xr[2 * i + 1], xr[2 * i + 2], xr[2 * i + 3]);
      const uint4 cst = lds4(par + PAR_CONST);
      const float A1 = __uint_as_float(cst.x), A2 = __uint_as_float(cst.z);
      uint32_t n = 0;
      early = false; wait1 = false;
#pragma unroll 1
      while (true) {
        uint32_t miss;
        asm volatile("{ .reg .pred p0, p1, p2, p3; .reg .b64 u, v; .reg .b128 w;\n"
                     "setp.ge.u32 p0, %22, 2; setp.ne.and.u32 p0, %4, %21, p0; setp.ne.u32 p1, %8, %21; setp.ne.u32 p2, %12, %21; setp.ne.u32 p3, %16, %21;\n"
                     "@p0 ld.relaxed.gpu.global.v4.u32 {%1, %2, %3, %4}, [%17];\n"
                     "@p1 ld.relaxed.gpu.global.v4.u32 {%5, %6, %7, %8}, [%18];\n"
                     "@p2 ld.relaxed.gpu.global.v4.u32 {%9, %10, %11, %12}, [%19];\n"
                     "@p3 ld.relaxed.gpu.global.v4.u32 {%13, %14, %15, %16}, [%20];\n"
                     "or.pred p0, p0, p1; or.pred p2, p2, p3; or.pred p0, p0, p2; vote.sync.any.pred p0, p0, 0xffffffff; selp.u32 %0, 1, 0, p0; }"
                     : "=r"(miss), "+r"(sv[0].x), "+r"(sv[0].y), "+r"(sv[0].z), "+r"(sv[0].w), "+r"(sv[1].x), "+r"(sv[1].y), "+r"(sv[1].z), "+r"(sv[1].w),
                       "+r"(sv[2].x), "+r"(sv[2].y), "+r"(sv[2].z), "+r"(sv[2].w), "+r"(sv[3].x), "+r"(sv[3].y), "+r"(sv[3].z), "+r"(sv[3].w)
                     : "l"(sp[0]), "l"(sp[1]), "l"(sp[2]), "l"(sp[3]), "r"(tag), "r"(tq) : "memory");
        if (!miss) break;
        wait1 = true;
        if (!early && (b >= NFFN || __all_sync(0xffffffffu, mbar_test(bar_box + (warp >> 1) * 8, 0)))) {
          early = true;
          LOAD_WF(0);
          __syncwarp();
          mbar_arrive_pred(bar_gate, lane0);
        }
        watchdog(n);
      }
      const uint4 v0 = tq < 2 ? own : sv[0], v1 = sv[1], v2 = sv[2], v3 = sv[3];
      PROF(8, ct == PT, 30); STAMP(6);
      float su = (__uint_as_float(v0.x) + __uint_as_float(v1.x)) + (__uint_as_float(v2.x) + __uint_as_float(v3.x));
      float sq = (__uint_as_float(v0.y) + __uint_as_float(v1.y)) + (__uint_as_float(v2.y) + __uint_as_float(v3.y));
      float dt = (__uint_as_float(v0.z) + __uint_as_float(v1.z)) + (__uint_as_float(v2.z) + __uint_as_float(v3.z));
      su += __shfl_xor_sync(0xffffffffu, su, 2); sq += __shfl_xor_sync(0xffffffffu, sq, 2); dt += __shfl_xor_sync(0xffffffffu, dt, 2);
      const float m = su * (1.f / DM);
      float mb, sd;
      ln_scalars(m, fmaxf(sq * (1.f / DM) - m * m, 0.f), mb, sd);
      const float inv = rcp(sd);
      rbest = (dt - mb * A1) * inv + A2;
      mm = pack_bf(mb, mb);
      ih = pack_bf(inv, inv);
      const float lo = inv - bf_lo(ih);
      il = pack_bf(lo, lo);
    }
    int ibest;
    {
      const uint32_t bits = __float_as_uint(rbest);
      const uint32_t key = (((int)bits < 0 ? ~bits : bits | 0x80000000u) & ~0x1ffu) | ((127 - lrow0 - (tq & 1) * 8) << 2) | tag;
      sts1(par + PAR_RED + warp * 4, __reduce_max_sync(0xffffffffu, key));
      PROF(8, ct == PT, 38); STAMP(7);
      uint32_t waited;
      asm volatile("{ .reg .pred p, q; setp.ne.u32 p, %1, 0; barrier.cta.red.or.pred q, 1, 256, p; selp.u32 %0, 1, 0, q; }" : "=r"(waited) : "r"((uint32_t)(wait1 && (wg || CW0))) : "memory");
      const uint4 ka = lds4(par + PAR_RED), kb = lds4(par + PAR_RED + 16);
      const uint32_t k2 = max(max(max(ka.x, ka.y), max(ka.z, ka.w)), max(max(kb.x, kb.y), max(kb.z, kb.w)));
      if (ct == 0 && ((cj & CWM) == 0 || (CWL && !waited))) st_relaxed(g_cand + rb, k2);
      ibest = 127 - ((k2 >> 2) & 127);
    }
    PROF(8, ct == PT, 39); STAMP(8);
    if ((ibest >> 4) == warp) {
      const int src = (ibest & 7) * 4 + ((ibest >> 3) & 1), ch = g * 2;
      const uint32_t cm = __shfl_sync(0xffffffffu, mm, src), ch_ = __shfl_sync(0xffffffffu, ih, src), cl = __shfl_sync(0xffffffffu, il, src);
      const uint32_t xa = res + (ch >> 3) * 16384 + ibest * 128 + (((ch & 7) ^ (ibest & 7)) << 4) + tq * 4;
      const uint32_t x0 = lds1(xa), x1 = lds1(xa ^ 16);
      const uint2 p0 = lds2(par + PAR_T2 + ch * 64 + tq * 16), p1 = lds2(par + PAR_T2 + ch * 64 + 64 + tq * 16);
      uint32_t* dst = g_row + rb * 2 * DM + cj * 128 + ln * 4;
      st_pairs(dst, ln_mod(x0, cm, ch_, cl, p0.x, p0.y), ln_mod(x1, cm, ch_, cl, p1.x, p1.y), tag);
      st_pairs(dst + DM, x0, x1, tag);
      __syncwarp();
    }
    PROF(8, ct == PT, 37); STAMP(9);
    uint32_t wd[64];
    const uint32_t wda = base + unit_of(FT_D, warp >> 1) + (warp & 1) * 8192 + frow * 128 + ((((ln >> 3) & 1) ^ (ln & 7)) << 4);
#define LOAD_WD(f) ldmatrix4t((wda ^ ((((f) >> 1) & 3) * 32)) + ((f) >> 3) * 4096 + ((f) & 1) * 2048, wd[4 * (f)], wd[4 * (f) + 1], wd[4 * (f) + 2], wd[4 * (f) + 3])
    if (!early) {
      if (b < NFFN) mbar_wait(bar_box + (warp >> 1) * 8, 0);
      LOAD_WF(0);
      __syncwarp();
      mbar_arrive_pred(bar_gate, lane0);
    }
    if (b < NFFN) {
      const uint32_t own = base + unit_of(FT_G, warp >> 1) + (warp & 1) * 8192;
      mbar_wait(bar_box + (4 + (warp >> 1)) * 8, 0);
      LOAD_WF(1);
      uint32_t* const ydst = g_ypart + ((size_t)(warp * 16 + tq * 2) * NFFN + b) * 8 + g;
      PROF(8, ct == PT, 31); STAMP(10);
      mbar_wait(bar_box + (8 + (warp >> 1)) * 8, 0);
#pragma unroll
      for (int f = 0; f < WDE; f++) LOAD_WD(f);
      STAMP(11);
      mbar_wait(bar_sel, 0);
      PROF(8, ct == PT, 33); STAMP(12);
      float d[8][4];
#pragma unroll
      for (int i = 0; i < 4; i++) { d[i][0] = 0.f; d[i][1] = 0.f; d[i][2] = 0.f; d[i][3] = 0.f; }
#pragma unroll
      for (int ks = 0; ks < 8; ks++) {
        const uint2 hb = lds2(own + 256 + ks * 32 + tq * 8);
#pragma unroll
        for (int mt = 0; mt < 4; mt++) {
          const int r = ks * 16 + mt * 4;
          mma16816(d[mt], wf[r], wf[r + 1], wf[r + 2], wf[r + 3], hb.x, hb.y);
        }
      }
      sts2(own + (tq * 8 + g) * 8, __float_as_uint((tq & 2) ? ((tq & 1) ? d[1][2] : d[1][0]) : ((tq & 1) ? d[0][2] : d[0][0])),
           __float_as_uint((tq & 2) ? ((tq & 1) ? d[3][2] : d[3][0]) : ((tq & 1) ? d[2][2] : d[2][0])));
      bar_sync(1, 256);
      uint32_t ab[4];
      {
        float G = 0.f, U = 0.f;
        uint2 pv[8];
#pragma unroll
        for (int w8 = 0; w8 < 8; w8++) pv[w8] = lds2(base + ln * 8 + ((FT_G >> (w8 >> 1) * 4) & 15) * UNIT + (w8 & 1) * 8192);
#pragma unroll
        for (int w8 = 0; w8 < 8; w8 += 2) {
          G += __uint_as_float(pv[w8].x) + __uint_as_float(pv[w8 + 1].x);
          U += __uint_as_float(pv[w8].y) + __uint_as_float(pv[w8 + 1].y);
        }
#pragma unroll
        for (int f = WDE; f < 16; f++) LOAD_WD(f);
        const float act = rbf(silu_f(rbf(G))) * rbf(U);
        const uint32_t pk = pack_bf(act, __shfl_down_sync(0xffffffffu, act, 1));
#pragma unroll
        for (int i = 0; i < 4; i++) ab[i] = __shfl_sync(0xffffffffu, pk, i * 8 + tq * 2);
      }
      PROF(8, ct == PT, 34); STAMP(13);
#pragma unroll
      for (int mt = 0; mt < 8; mt++) {
        d[mt][0] = 0.f; d[mt][1] = 0.f; d[mt][2] = 0.f; d[mt][3] = 0.f;
        mma16816(d[mt], wd[mt * 8], wd[mt * 8 + 1], wd[mt * 8 + 2], wd[mt * 8 + 3], ab[0], ab[1]);
        mma16816(d[mt], wd[mt * 8 + 4], wd[mt * 8 + 5], wd[mt * 8 + 6], wd[mt * 8 + 7], ab[2], ab[3]);
      }
#pragma unroll
      for (int i = 0; i < 4; i++) {
        const int m4 = (i >> 1) * 4, e = (i & 1) * 2;
        const float y = (tq & 2) ? ((tq & 1) ? d[m4 + 3][e] : d[m4 + 2][e]) : ((tq & 1) ? d[m4 + 1][e] : d[m4][e]);
        st_relaxed(ydst + (m4 * 2 + (i & 1)) * NFFN * 8, tagf(y, tag));
      }
      PROF(8, ct == PT, 35); STAMP(14);
    }
    mbar_wait(bar_sel, 0);
    mbar_arrive_pred(bar_win, ct == 0);
    const int iwin = lds1(par + PAR_CONST + 60) & 0x7ff;
    {
      const uint32_t mm0 = __shfl_sync(0xffffffffu, mm, ln & ~1), mm1 = __shfl_sync(0xffffffffu, mm, ln | 1);
      const uint32_t ih0 = __shfl_sync(0xffffffffu, ih, ln & ~1), ih1 = __shfl_sync(0xffffffffu, ih, ln | 1);
      const uint32_t il0 = __shfl_sync(0xffffffffu, il, ln & ~1), il1 = __shfl_sync(0xffffffffu, il, ln | 1);
      const bool mine = (iwin >> 4) == rb * 8 + warp;
#pragma unroll 1
      for (int hf = 0; hf < 2; hf++) {
        uint32_t x[16];
#pragma unroll
        for (int i = 0; i < 8; i += 2) ldmatrix4((trow ^ (i << 4)) + hf * 16384, x[2 * i], x[2 * i + 1], x[2 * i + 2], x[2 * i + 3]);
#pragma unroll
        for (int i = 0; i < 8; i++) {
          const uint4 pv = lds4(par + PAR_T2 + (hf * 8 + i) * 64 + tq * 16);
          x[2 * i] = hadd2(x[2 * i], hmul2(pv.z, ln_mod(x[2 * i], mm0, ih0, il0, pv.x, pv.y)));
          x[2 * i + 1] = hadd2(x[2 * i + 1], hmul2(pv.z, ln_mod(x[2 * i + 1], mm1, ih1, il1, pv.x, pv.y)));
        }
        if (mine) {
          uint32_t* dst = reinterpret_cast<uint32_t*>(P.out + (size_t)grow0 * DM + cj * 128 + hf * 64) + tq;
#pragma unroll
          for (int i = 0; i < 8; i++) {
            if (grow0 != iwin) dst[i * 4] = x[2 * i];
            if (grow0 + 8 != iwin) dst[i * 4 + 4 * DM] = x[2 * i + 1];
          }
        } else {
#pragma unroll
          for (int i = 0; i < 8; i += 2) stmatrix4((trow ^ (i << 4)) + hf * 16384, x[2 * i], x[2 * i + 1], x[2 * i + 2], x[2 * i + 3]);
          fence_async_smem();
          __syncwarp();
          if (elect_one()) {
            tma2d_store(&maps.out, res + hf * 16384 + warp * 2048, cj * 128 + hf * 64, rb * 128 + warp * 16);
            asm volatile("cp.async.bulk.commit_group;" ::: "memory");
          }
        }
      }
      asm volatile("cp.async.bulk.wait_group.read 0;" ::: "memory");
    }
    PROF(8, ct == PT, 11); STAMP(15);
    cluster_wait();
  }
}

typedef CUresult (*EncodeFn)(CUtensorMap*, CUtensorMapDataType, cuuint32_t, void*, const cuuint64_t*, const cuuint64_t*,
                             const cuuint32_t*, const cuuint32_t*, CUtensorMapInterleave, CUtensorMapSwizzle,
                             CUtensorMapL2promotion, CUtensorMapFloatOOBfill);

void map2d(EncodeFn enc, CUtensorMap* m, const void* p, uint64_t rows, uint64_t cols, uint32_t brows) {
  cuuint64_t dims[2] = {cols, rows}, strides[1] = {cols * 2};
  cuuint32_t box[2] = {64, brows}, es[2] = {1, 1};
  enc(m, CU_TENSOR_MAP_DATA_TYPE_BFLOAT16, 2, const_cast<void*>(p), dims, strides, box, es, CU_TENSOR_MAP_INTERLEAVE_NONE,
      CU_TENSOR_MAP_SWIZZLE_128B, CU_TENSOR_MAP_L2_PROMOTION_L2_256B, CU_TENSOR_MAP_FLOAT_OOB_FILL_NONE);
}
void map2d_narrow(EncodeFn enc, CUtensorMap* m, const void* p, uint64_t rows, uint64_t cols) {
  cuuint64_t dims[2] = {cols, rows}, strides[1] = {cols * 2};
  cuuint32_t box[2] = {32, 256}, es[2] = {1, 1};
  enc(m, CU_TENSOR_MAP_DATA_TYPE_BFLOAT16, 2, const_cast<void*>(p), dims, strides, box, es, CU_TENSOR_MAP_INTERLEAVE_NONE,
      CU_TENSOR_MAP_SWIZZLE_64B, CU_TENSOR_MAP_L2_PROMOTION_L2_64B, CU_TENSOR_MAP_FLOAT_OOB_FILL_NONE);
}
void map3d(EncodeFn enc, CUtensorMap* m, const void* p, uint64_t rows, uint64_t cols, uint32_t brows, uint32_t nch) {
  cuuint64_t dims[3] = {64, rows, cols / 64}, strides[2] = {cols * 2, 128};
  cuuint32_t box[3] = {64, brows, nch}, es[3] = {1, 1, 1};
  enc(m, CU_TENSOR_MAP_DATA_TYPE_BFLOAT16, 3, const_cast<void*>(p), dims, strides, box, es, CU_TENSOR_MAP_INTERLEAVE_NONE,
      CU_TENSOR_MAP_SWIZZLE_128B, CU_TENSOR_MAP_L2_PROMOTION_L2_256B, CU_TENSOR_MAP_FLOAT_OOB_FILL_NONE);
}

}

extern "C" void kernel_launch(void* const* d_in, const int* in_sizes, int n_in, void* d_out, int out_size) {
  (void)in_sizes; (void)n_in; (void)out_size;
  static EncodeFn enc = nullptr;
  if (!enc) {
    void* fn = nullptr;
    cudaDriverEntryPointQueryResult st;
    cudaGetDriverEntryPoint("cuTensorMapEncodeTiled", &fn, cudaEnableDefault, &st);
    enc = (EncodeFn)fn;
    cudaFuncSetAttribute(fused_kernel, cudaFuncAttributeMaxDynamicSharedMemorySize, SMEM_BYTES);
  }
  Maps maps;
  map2d(enc, &maps.x, d_in[0], SEQ, DM, 128);
  map2d(enc, &maps.out, d_out, SEQ, DM, 16);
  map3d(enc, &maps.wq, d_in[3], DM, NQ, 64, 2);
  map3d(enc, &maps.k, d_in[1], 4 * SK, 128, 128, 1);
  map3d(enc, &maps.v, d_in[2], 4 * SK, 128, 128, 1);
  map3d(enc, &maps.wo, d_in[4], NQ, DM, 64, 2);
  map2d_narrow(enc, &maps.wg, d_in[7], DM, FF);
  map2d_narrow(enc, &maps.wu, d_in[8], DM, FF);
  map3d(enc, &maps.wd, d_in[9], FF, DM, 32, 4);
  map2d_narrow(enc, &maps.wm, d_in[11], DM, NMOD);
  Ptrs p;
  p.x = (const __nv_bfloat16*)d_in[0];
  p.w_r = (const __nv_bfloat16*)d_in[6];
  p.w_gate = (const __nv_bfloat16*)d_in[7];
  p.w_up = (const __nv_bfloat16*)d_in[8];
  p.w_down = (const __nv_bfloat16*)d_in[9];
  p.c = (const __nv_bfloat16*)d_in[10];
  p.w_mod = (const __nv_bfloat16*)d_in[11];
  p.out = (__nv_bfloat16*)d_out;
  fused_kernel<<<NMAIN + NHELP, 384, SMEM_BYTES>>>(maps, p);
}
```

```cpp
#include <cuda_runtime.h>
#include <cuda_bf16.h>
#include <cuda.h>
#include <stdint.h>
#include <type_traits>

#define HD 1
#define HDX 2
#define XF 4
#define XE 32
#define XR 0
#define PF2 1
#define PF2T 4
#define NRS 6
#define FPACE 3
#define GOST 20
#define WB 2
#define WN 24
#define RES0 17
#define RES1 20
#define HU 32
#define NS1 6
#define PD0 40
#define PG0 31
#define PSL 0
#define CWM 7
#define WDE 16
#define CWL 1
#define CW0 0
#define ESV 1
#define PPOS 1
#define FB0 0
#define FB2 8
#define VREL 7
#define E0 3

namespace {

constexpr int SEQ = 2048, DM = 1024, NQ = 4096, SK = 2048, WIN = 512, FF = 3584, NMOD = 6144;
constexpr int NMAIN = 128, NHELP = 4, NFFN = 112;
constexpr int NSLOT = 4, SLOT_BYTES = 32768, UNIT = 16384, GST_BYTES = 3 * UNIT;
constexpr uint32_t XT0 = 0x9630, XT1 = 0x54DC, XT2 = 0xDC96;
constexpr uint32_t WT0 = 0xA741, WT1 = 0x720A, WT2 = 0x20A7;
constexpr uint32_t AT0 = 0x7420, AT1 = 0x2C0A;
constexpr uint32_t QT = 0x549696DC;
constexpr int OFF_STAGE = 12 * UNIT;
constexpr uint32_t FT_G = 0x761B, FT_U = 0x0CA9, FT_D = 0x382D;
constexpr int OFF_RES = 4 * UNIT;
constexpr int OFF_PAR = 14 * UNIT;
constexpr int OFF_BAR = OFF_PAR + 2048 + 512;
constexpr int SMEM_BYTES = OFF_BAR + 512;
static_assert(SMEM_BYTES <= 232448, "smem");

constexpr int PAR_T1 = 0;
constexpr int PAR_T2 = 512;
constexpr int PAR_CONST = 1536;
constexpr int PAR_RED = 1600;
constexpr int PAR_SINK = 2176;

struct Maps {
  CUtensorMap x, wq, k, v, wo, wg, wu, wd, wm, out;
};
struct Ptrs {
  const __nv_bfloat16 *x, *w_r, *c, *w_mod, *w_gate, *w_up, *w_down;
  __nv_bfloat16* out;
};

__device__ __align__(1024) uint8_t g_act[16 * 80 * UNIT];
__device__ __align__(128) uint32_t g_mod[NMOD];
__device__ __align__(128) uint32_t g_modp[2 * 2 * DM];
__device__ __align__(128) uint32_t g_ln1[SEQ * 4];
__device__ __align__(128) uint32_t g_cnt_h[16 * 32];
__device__ __align__(128) uint32_t g_cnt_o[128 * 32];
__device__ __align__(128) uint32_t g_xch[NMAIN * 8 * 256 * 4];
__device__ __align__(128) uint32_t g_stats[8 * SEQ * 4];
__device__ __align__(128) uint32_t g_cand[32];
__device__ __align__(128) uint32_t g_row[16 * 2 * DM];
__device__ __align__(128) uint32_t g_ypart[NMAIN * NFFN * 8];
__device__ uint32_t g_epoch;

__device__ __forceinline__ uint32_t fresh_lane() { uint32_t l; asm volatile("mov.u32 %0, %%laneid;" : "=r"(l)); return l; }
__device__ __forceinline__ uint32_t frag_offset(int warp) {
  const uint32_t l = fresh_lane();
  return ((warp & 3) * 16 + (l & 15)) * 128 + (((l >> 4) ^ (l & 7)) << 4);
}
__device__ __forceinline__ bool elect_one() {
  uint32_t p;
  asm volatile("{ .reg .pred q; elect.sync _|q, 0xffffffff; selp.u32 %0, 1, 0, q; }" : "=r"(p));
  return p;
}
__device__ __forceinline__ uint32_t smem_u32(const void* p) { return (uint32_t)__cvta_generic_to_shared(p); }
__device__ __forceinline__ void mbar_init(uint32_t bar, uint32_t cnt) {
  asm volatile("mbarrier.init.shared::cta.b64 [%0], %1;" ::"r"(bar), "r"(cnt) : "memory");
}
__device__ __forceinline__ void mbar_expect_tx(uint32_t bar, uint32_t bytes) {
  asm volatile("mbarrier.arrive.expect_tx.shared::cta.b64 _, [%0], %1;" ::"r"(bar), "r"(bytes) : "memory");
}
__device__ __forceinline__ void mbar_arrive(uint32_t bar) {
  asm volatile("mbarrier.arrive.shared::cta.b64 _, [%0];" ::"r"(bar) : "memory");
}
__device__ __forceinline__ void mbar_arrive_pred(uint32_t bar, bool p) {
  asm volatile("{ .reg .pred p; setp.ne.b32 p, %1, 0; @p mbarrier.arrive.shared::cta.b64 _, [%0]; }" ::"r"(bar), "r"((int)p) : "memory");
}
__device__ __forceinline__ void mbar_arrive_cl(uint32_t bar, uint32_t off, bool p = true) {
  asm volatile("{ .reg .pred p, q; .reg .b32 a; setp.ne.b32 q, %2, 0; setp.ne.and.b32 p, %0, 0, q; add.u32 a, %0, %1; @p mbarrier.arrive.shared::cluster.b64 _, [a]; }"
               ::"r"(bar), "r"(off), "r"((int)p) : "memory");
}
__device__ __forceinline__ uint32_t mapa(uint32_t addr, uint32_t cta) {
  uint32_t r; asm("mapa.shared::cluster.u32 %0, %1, %2;" : "=r"(r) : "r"(addr), "r"(cta)); return r;
}
__device__ __forceinline__ void cluster_arrive() { asm volatile("barrier.cluster.arrive.relaxed.aligned;" ::: "memory"); }
__device__ __forceinline__ void cluster_wait() { asm volatile("barrier.cluster.wait.aligned;" ::: "memory"); }
__device__ __forceinline__ void watchdog(uint32_t& n) {
}
__device__ __forceinline__ void mbar_wait(uint32_t bar, uint32_t parity) {
  asm volatile("{\n.reg .pred p;\nWAIT_%=:\nmbarrier.try_wait.parity.shared::cta.b64 p, [%0], %1;\n@!p bra WAIT_%=;\n}" ::"r"(bar), "r"(parity) : "memory");
}
__device__ __forceinline__ bool mbar_test(uint32_t bar, uint32_t parity) {
  uint32_t ok;
  asm volatile("{\n.reg .pred p;\nmbarrier.test_wait.parity.shared::cta.b64 p, [%1], %2;\nselp.u32 %0, 1, 0, p;\n}" : "=r"(ok) : "r"(bar), "r"(parity) : "memory");
  return ok;
}
__device__ __forceinline__ uint64_t l2_stream() {
  uint64_t f; asm("createpolicy.fractional.L2::evict_first.b64 %0, 1.0;" : "=l"(f)); return f;
}
__device__ __forceinline__ void tma2d(uint32_t dst, const CUtensorMap* m, int c0, int c1, uint32_t bar) {
  asm volatile("cp.async.bulk.tensor.2d.shared::cluster.global.mbarrier::complete_tx::bytes.L2::cache_hint [%0], [%1, {%3, %4}], [%2], %5;"
               ::"r"(dst), "l"(m), "r"(bar), "r"(c0), "r"(c1), "l"(l2_stream()) : "memory");
}
__device__ __forceinline__ void tma3d_prefetch(const CUtensorMap* m, int c0, int c1, int c2) {
  asm volatile("cp.async.bulk.prefetch.tensor.3d.L2.global.tile [%0, {%1, %2, %3}];" ::"l"(m), "r"(c0), "r"(c1), "r"(c2) : "memory");
}
__device__ __forceinline__ void bulk_load(uint32_t dst, const void* src, uint32_t bytes, uint32_t bar) {
  asm volatile("cp.async.bulk.shared::cluster.global.mbarrier::complete_tx::bytes [%0], [%1], %2, [%3];" ::"r"(dst), "l"(src), "r"(bytes), "r"(bar) : "memory");
}
__device__ __forceinline__ void bulk_load_stream(uint32_t dst, const void* src, uint32_t bytes, uint32_t bar) {
  asm volatile("cp.async.bulk.shared::cluster.global.mbarrier::complete_tx::bytes.L2::cache_hint [%0], [%1], %2, [%3], %4;"
               ::"r"(dst), "l"(src), "r"(bytes), "r"(bar), "l"(l2_stream()) : "memory");
}
__device__ __forceinline__ void tma2d_store(const CUtensorMap* m, uint32_t src, int c0, int c1) {
  asm volatile("cp.async.bulk.tensor.2d.global.shared::cta.bulk_group [%0, {%2, %3}], [%1];" ::"l"(m), "r"(src), "r"(c0), "r"(c1) : "memory");
}
__device__ __forceinline__ void bulk_store(void* dst, uint32_t src, uint32_t bytes) {
  asm volatile("cp.async.bulk.global.shared::cta.bulk_group [%0], [%1], %2;" ::"l"(dst), "r"(src), "r"(bytes) : "memory");
}
__device__ __forceinline__ uint32_t unit_of(uint32_t table, uint32_t i) { return ((table >> (i * 4)) & 15) * UNIT; }
__device__ __forceinline__ void tma3d(uint32_t dst, const CUtensorMap* m, int c0, int c1, int c2, uint32_t bar) {
  asm volatile("cp.async.bulk.tensor.3d.shared::cluster.global.mbarrier::complete_tx::bytes.L2::cache_hint [%0], [%1, {%3, %4, %5}], [%2], %6;"
               ::"r"(dst), "l"(m), "r"(bar), "r"(c0), "r"(c1), "r"(c2), "l"(l2_stream()) : "memory");
}
template <bool STREAM>
__device__ __forceinline__ void tma3d_mc(uint32_t dst, const CUtensorMap* m, int c0, int c1, int c2, uint32_t bar) {
  if (STREAM)
    asm volatile("cp.async.bulk.tensor.3d.shared::cluster.global.mbarrier::complete_tx::bytes.multicast::cluster.L2::cache_hint [%0], [%1, {%3, %4, %5}], [%2], %6, %7;"
                 ::"r"(dst), "l"(m), "r"(bar), "r"(c0), "r"(c1), "r"(c2), "h"((uint16_t)3), "l"(l2_stream()) : "memory");
  else
    asm volatile("cp.async.bulk.tensor.3d.shared::cluster.global.mbarrier::complete_tx::bytes.multicast::cluster [%0], [%1, {%3, %4, %5}], [%2], %6;"
                 ::"r"(dst), "l"(m), "r"(bar), "r"(c0), "r"(c1), "r"(c2), "h"((uint16_t)3) : "memory");
}
__device__ __forceinline__ void prefetch_map(const CUtensorMap* m) {
  asm volatile("prefetch.tensormap [%0];" ::"l"(m) : "memory");
}
__device__ __forceinline__ void fence_async() { asm volatile("fence.proxy.async.global;" ::: "memory"); }
__device__ __forceinline__ void fence_async_smem() { asm volatile("fence.proxy.async.shared::cta;" ::: "memory"); }
__device__ __forceinline__ void bar_sync(int id, int n) { asm volatile("bar.sync %0, %1;" ::"r"(id), "r"(n) : "memory"); }
__device__ __forceinline__ void bar_arrive(int id, int n) { asm volatile("bar.arrive %0, %1;" ::"r"(id), "r"(n) : "memory"); }
__device__ __forceinline__ void wg_fence() { asm volatile("wgmma.fence.sync.aligned;" ::: "memory"); }
__device__ __forceinline__ void wg_commit() { asm volatile("wgmma.commit_group.sync.aligned;" ::: "memory"); }
template <int N> __device__ __forceinline__ void wg_wait() { asm volatile("wgmma.wait_group.sync.aligned %0;" ::"n"(N) : "memory"); }
__device__ __forceinline__ uint64_t make_desc(uint32_t addr, uint32_t lbo, uint32_t sbo) {
  return (uint64_t)((addr & 0x3FFFF) >> 4) | ((uint64_t)(lbo >> 4) << 16) | ((uint64_t)(sbo >> 4) << 32) | (1ull << 62);
}
__device__ __forceinline__ uint32_t ld_relaxed(const uint32_t* p) {
  uint32_t v; asm volatile("ld.relaxed.gpu.global.u32 %0, [%1];" : "=r"(v) : "l"(p) : "memory"); return v;
}
__device__ __forceinline__ uint32_t ld_acquire(const uint32_t* p) {
  uint32_t v; asm volatile("ld.acquire.gpu.global.u32 %0, [%1];" : "=r"(v) : "l"(p) : "memory"); return v;
}
__device__ __forceinline__ uint4 ld_relaxed4(const uint32_t* p) {
  uint4 v; asm volatile("ld.relaxed.gpu.global.v4.u32 {%0,%1,%2,%3}, [%4];" : "=r"(v.x), "=r"(v.y), "=r"(v.z), "=r"(v.w) : "l"(p) : "memory"); return v;
}
__device__ __forceinline__ uint2 ld_relaxed2(const uint32_t* p) {
  uint2 v; asm volatile("ld.relaxed.gpu.global.v2.u32 {%0,%1}, [%2];" : "=r"(v.x), "=r"(v.y) : "l"(p) : "memory"); return v;
}
__device__ __forceinline__ void st_relaxed(uint32_t* p, uint32_t v) {
  asm volatile("st.relaxed.gpu.global.u32 [%0], %1;" ::"l"(p), "r"(v) : "memory");
}
__device__ __forceinline__ void st_relaxed2(uint32_t* p, uint32_t a, uint32_t b) {
  asm volatile("st.relaxed.gpu.global.v2.u32 [%0], {%1,%2};" ::"l"(p), "r"(a), "r"(b) : "memory");
}
__device__ __forceinline__ void st_relaxed4(uint32_t* p, uint32_t a, uint32_t b, uint32_t c, uint32_t d) {
  asm volatile("st.relaxed.gpu.global.v4.u32 [%0], {%1,%2,%3,%4};" ::"l"(p), "r"(a), "r"(b), "r"(c), "r"(d) : "memory");
}
__device__ __forceinline__ void st_b128(uint32_t* p, uint32_t a, uint32_t b, uint32_t c, uint32_t d) {
  asm volatile("{ .reg .b64 u, v; .reg .b128 w; mov.b64 u, {%1, %2}; mov.b64 v, {%3, %4}; mov.b128 w, {u, v}; st.relaxed.gpu.global.b128 [%0], w; }"
               ::"l"(p), "r"(a), "r"(b), "r"(c), "r"(d) : "memory");
}
__device__ __forceinline__ uint4 ld_b128(const uint32_t* p) {
  uint4 r;
  asm volatile("{ .reg .b64 u, v; .reg .b128 w; ld.relaxed.gpu.global.b128 w, [%4]; mov.b128 {u, v}, w; mov.b64 {%0, %1}, u; mov.b64 {%2, %3}, v; }"
               : "=r"(r.x), "=r"(r.y), "=r"(r.z), "=r"(r.w) : "l"(p) : "memory");
  return r;
}
__device__ __forceinline__ void st_pairs(uint32_t* p, uint32_t a, uint32_t b, uint32_t tag) {
  asm volatile("{ .reg .b64 u, v; mov.b64 u, {%1, %3}; mov.b64 v, {%2, %3}; st.relaxed.gpu.global.v2.b64 [%0], {u, v}; }"
               ::"l"(p), "r"(a), "r"(b), "r"(tag) : "memory");
}
__device__ __forceinline__ uint4 ld_pairs(const uint32_t* p) {
  uint4 v;
  asm volatile("{ .reg .b64 u, v; ld.relaxed.gpu.global.v2.b64 {u, v}, [%4]; mov.b64 {%0, %1}, u; mov.b64 {%2, %3}, v; }"
               : "=r"(v.x), "=r"(v.y), "=r"(v.z), "=r"(v.w) : "l"(p) : "memory");
  return v;
}
__device__ __forceinline__ uint2 ld_pair(const uint32_t* p) {
  uint2 v;
  asm volatile("{ .reg .b64 u; ld.relaxed.gpu.global.b64 u, [%2]; mov.b64 {%0, %1}, u; }" : "=r"(v.x), "=r"(v.y) : "l"(p) : "memory");
  return v;
}
__device__ __forceinline__ void red_release(uint32_t* p, uint32_t v) {
  asm volatile("red.release.gpu.global.add.u32 [%0], %1;" ::"l"(p), "r"(v) : "memory");
}
__device__ __forceinline__ uint32_t ldg_nc1(const void* p) {
  uint32_t v;
  asm volatile("ld.global.nc.u32 %0, [%1];" : "=r"(v) : "l"(p));
  return v;
}
__device__ __forceinline__ uint4 ldg_nc4(const void* p) {
  uint4 v; asm volatile("ld.global.nc.L1::no_allocate.v4.u32 {%0,%1,%2,%3}, [%4];" : "=r"(v.x), "=r"(v.y), "=r"(v.z), "=r"(v.w) : "l"(p)); return v;
}
__device__ __forceinline__ uint4 ldg_stream4(const void* p) {
  uint4 v;
  asm volatile("ld.global.nc.L1::no_allocate.L2::cache_hint.v4.u32 {%0,%1,%2,%3}, [%4], %5;" : "=r"(v.x), "=r"(v.y), "=r"(v.z), "=r"(v.w) : "l"(p), "l"(l2_stream()));
  return v;
}
__device__ __forceinline__ void stg4(void* p, uint4 v) {
  asm volatile("st.global.v4.u32 [%0], {%1,%2,%3,%4};" ::"l"(p), "r"(v.x), "r"(v.y), "r"(v.z), "r"(v.w) : "memory");
}
__device__ __forceinline__ void wait_counter(const uint32_t* p, uint32_t target) {
  uint32_t n = 0;
  while ((int)(ld_acquire(p) - target) < 0) { watchdog(n); }
}
__device__ __forceinline__ uint32_t tagf(float v, uint32_t tag) { return (__float_as_uint(v) & ~3u) | tag; }
__device__ __forceinline__ bool tag_ok(uint4 v, uint32_t tag) { return (((v.x ^ tag) | (v.y ^ tag) | (v.z ^ tag) | (v.w ^ tag)) & 3u) == 0; }
__device__ __forceinline__ float untag_sum(uint32_t a, uint32_t b) { return __uint_as_float(a & ~3u) + __uint_as_float(b & ~3u); }
__device__ __forceinline__ uint4 poll4(const uint32_t* p, uint32_t tag) {
  uint4 v = ld_relaxed4(p);
  uint32_t n = 0;
  while (!tag_ok(v, tag)) { v = ld_relaxed4(p); watchdog(n); }
  return v;
}
__device__ __forceinline__ float bf_lo(uint32_t v) { return __uint_as_float(v << 16); }
__device__ __forceinline__ float bf_hi(uint32_t v) { return __uint_as_float(v & 0xffff0000u); }
__device__ __forceinline__ uint32_t pack_bf(float lo, float hi) {
  uint32_t r; asm("cvt.rn.bf16x2.f32 %0, %1, %2;" : "=r"(r) : "f"(hi), "f"(lo)); return r;
}
__device__ __forceinline__ float rbf(float v) { return __uint_as_float(pack_bf(0.f, v) & 0xffff0000u); }
__device__ __forceinline__ uint32_t hmul2(uint32_t a, uint32_t b) {
  uint32_t r; asm("mul.rn.bf16x2 %0, %1, %2;" : "=r"(r) : "r"(a), "r"(b)); return r;
}
__device__ __forceinline__ uint32_t hadd2(uint32_t a, uint32_t b) {
  uint32_t r; asm("add.rn.bf16x2 %0, %1, %2;" : "=r"(r) : "r"(a), "r"(b)); return r;
}
__device__ __forceinline__ uint32_t hsub2(uint32_t a, uint32_t b) {
  uint32_t r; asm("sub.rn.bf16x2 %0, %1, %2;" : "=r"(r) : "r"(a), "r"(b)); return r;
}
__device__ __forceinline__ uint32_t hmax2(uint32_t a, uint32_t b) {
  uint32_t r; asm("max.bf16x2 %0, %1, %2;" : "=r"(r) : "r"(a), "r"(b)); return r;
}
__device__ __forceinline__ float rcp(float x) { float r; asm("rcp.approx.ftz.f32 %0, %1;" : "=f"(r) : "f"(x)); return r; }
__device__ __forceinline__ float ex2(float x) { float r; asm("ex2.approx.ftz.f32 %0, %1;" : "=f"(r) : "f"(x)); return r; }
__device__ __forceinline__ void stmatrix4(uint32_t addr, uint32_t a, uint32_t b, uint32_t c, uint32_t d) {
  asm volatile("stmatrix.sync.aligned.m8n8.x4.shared.b16 [%0], {%1,%2,%3,%4};" ::"r"(addr), "r"(a), "r"(b), "r"(c), "r"(d) : "memory");
}
__device__ __forceinline__ void ldmatrix4(uint32_t addr, uint32_t& a, uint32_t& b, uint32_t& c, uint32_t& d) {
  asm volatile("ldmatrix.sync.aligned.m8n8.x4.shared.b16 {%0,%1,%2,%3}, [%4];" : "=r"(a), "=r"(b), "=r"(c), "=r"(d) : "r"(addr) : "memory");
}
__device__ __forceinline__ void ldmatrix4t(uint32_t addr, uint32_t& a, uint32_t& b, uint32_t& c, uint32_t& d) {
  asm volatile("ldmatrix.sync.aligned.m8n8.x4.trans.shared.b16 {%0,%1,%2,%3}, [%4];" : "=r"(a), "=r"(b), "=r"(c), "=r"(d) : "r"(addr) : "memory");
}
__device__ __forceinline__ void mma16816(float (&d)[4], uint32_t a0, uint32_t a1, uint32_t a2, uint32_t a3, uint32_t b0, uint32_t b1) {
  asm volatile("mma.sync.aligned.m16n8k16.row.col.f32.bf16.bf16.f32 {%0,%1,%2,%3}, {%4,%5,%6,%7}, {%8,%9}, {%0,%1,%2,%3};"
               : "+f"(d[0]), "+f"(d[1]), "+f"(d[2]), "+f"(d[3]) : "r"(a0), "r"(a1), "r"(a2), "r"(a3), "r"(b0), "r"(b1));
}
__device__ __forceinline__ void sts1(uint32_t a, uint32_t v) { asm volatile("st.shared.u32 [%0], %1;" ::"r"(a), "r"(v) : "memory"); }
__device__ __forceinline__ uint4 lds4(uint32_t a) {
  uint4 v; asm volatile("ld.shared.v4.u32 {%0,%1,%2,%3}, [%4];" : "=r"(v.x), "=r"(v.y), "=r"(v.z), "=r"(v.w) : "r"(a) : "memory"); return v;
}
__device__ __forceinline__ uint2 lds2(uint32_t a) {
  uint2 v; asm volatile("ld.shared.v2.u32 {%0,%1}, [%2];" : "=r"(v.x), "=r"(v.y) : "r"(a) : "memory"); return v;
}
__device__ __forceinline__ uint32_t lds1(uint32_t a) {
  uint32_t v; asm volatile("ld.shared.u32 %0, [%1];" : "=r"(v) : "r"(a) : "memory"); return v;
}
__device__ __forceinline__ void sts2(uint32_t a, uint32_t x, uint32_t y) { asm volatile("st.shared.v2.u32 [%0], {%1,%2};" ::"r"(a), "r"(x), "r"(y) : "memory"); }
__device__ __forceinline__ void sts4(uint32_t a, uint4 v) {
  asm volatile("st.shared.v4.u32 [%0], {%1,%2,%3,%4};" ::"r"(a), "r"(v.x), "r"(v.y), "r"(v.z), "r"(v.w) : "memory");
}
__device__ __forceinline__ float silu_f(float v) { return __fdividef(v, 1.f + __expf(-v)); }
__device__ __forceinline__ uint32_t hfma2(uint32_t a, uint32_t b, uint32_t c) {
  uint32_t r; asm("fma.rn.bf16x2 %0, %1, %2, %3;" : "=r"(r) : "r"(a), "r"(b), "r"(c)); return r;
}
__device__ __forceinline__ void split_inv(float sd, uint32_t& ih, uint32_t& il) {
  const float inv = rcp(sd);
  ih = pack_bf(inv, inv);
  const float lo = inv - bf_lo(ih);
  il = pack_bf(lo, lo);
}
__device__ __forceinline__ uint32_t ln_mod(uint32_t x, uint32_t mean2, uint32_t ih, uint32_t il, uint32_t c1, uint32_t sh) {
  const uint32_t d = hsub2(x, mean2);
  return hadd2(hmul2(hfma2(d, ih, hmul2(d, il)), c1), sh);
}

#define R8(a, i) "+f"(a[i]), "+f"(a[i + 1]), "+f"(a[i + 2]), "+f"(a[i + 3]), "+f"(a[i + 4]), "+f"(a[i + 5]), "+f"(a[i + 6]), "+f"(a[i + 7])
#define D64 "{%0,%1,%2,%3,%4,%5,%6,%7,%8,%9,%10,%11,%12,%13,%14,%15,%16,%17,%18,%19,%20,%21,%22,%23,%24,%25,%26,%27,%28,%29,%30,%31," \
            "%32,%33,%34,%35,%36,%37,%38,%39,%40,%41,%42,%43,%44,%45,%46,%47,%48,%49,%50,%51,%52,%53,%54,%55,%56,%57,%58,%59,%60,%61,%62,%63}"
template <int TB>
__device__ __forceinline__ void mma_ss(float (&d)[64], uint64_t da, uint64_t db, int sc) {
  asm volatile("{\n.reg .pred p;\nsetp.ne.b32 p, %66, 0;\n"
               "wgmma.mma_async.sync.aligned.m64n128k16.f32.bf16.bf16 " D64 ", %64, %65, p, 1, 1, 0, %67;\n}"
               : R8(d, 0), R8(d, 8), R8(d, 16), R8(d, 24), R8(d, 32), R8(d, 40), R8(d, 48), R8(d, 56)
               : "l"(da), "l"(db), "r"(sc), "n"(TB));
}
template <int TB>
__device__ __forceinline__ void mma_rs(float (&d)[64], uint32_t a0, uint32_t a1, uint32_t a2, uint32_t a3, uint64_t db, int sc) {
  asm volatile("{\n.reg .pred p;\nsetp.ne.b32 p, %69, 0;\n"
               "wgmma.mma_async.sync.aligned.m64n128k16.f32.bf16.bf16 " D64 ", {%64,%65,%66,%67}, %68, p, 1, 1, %70;\n}"
               : R8(d, 0), R8(d, 8), R8(d, 16), R8(d, 24), R8(d, 32), R8(d, 40), R8(d, 48), R8(d, 56)
               : "r"(a0), "r"(a1), "r"(a2), "r"(a3), "l"(db), "r"(sc), "n"(TB));
}
#define D128 "{%0,%1,%2,%3,%4,%5,%6,%7,%8,%9,%10,%11,%12,%13,%14,%15,%16,%17,%18,%19,%20,%21,%22,%23,%24,%25,%26,%27,%28,%29,%30,%31," \
             "%32,%33,%34,%35,%36,%37,%38,%39,%40,%41,%42,%43,%44,%45,%46,%47,%48,%49,%50,%51,%52,%53,%54,%55,%56,%57,%58,%59,%60,%61,%62,%63," \
             "%64,%65,%66,%67,%68,%69,%70,%71,%72,%73,%74,%75,%76,%77,%78,%79,%80,%81,%82,%83,%84,%85,%86,%87,%88,%89,%90,%91,%92,%93,%94,%95," \
             "%96,%97,%98,%99,%100,%101,%102,%103,%104,%105,%106,%107,%108,%109,%110,%111,%112,%113,%114,%115,%116,%117,%118,%119,%120,%121,%122,%123,%124,%125,%126,%127}"
#define R128(d, e) R8(d, 0), R8(d, 8), R8(d, 16), R8(d, 24), R8(d, 32), R8(d, 40), R8(d, 48), R8(d, 56), \
                   R8(e, 0), R8(e, 8), R8(e, 16), R8(e, 24), R8(e, 32), R8(e, 40), R8(e, 48), R8(e, 56)
__device__ __forceinline__ void mma256_ss(float (&d)[64], float (&e)[64], uint64_t da, uint64_t db, int sc) {
  asm volatile("{\n.reg .pred p;\nsetp.ne.b32 p, %130, 0;\n"
               "wgmma.mma_async.sync.aligned.m64n256k16.f32.bf16.bf16 " D128 ", %128, %129, p, 1, 1, 0, 1;\n}"
               : R128(d, e) : "l"(da), "l"(db), "r"(sc));
}
__device__ __forceinline__ void mma256_rs(float (&d)[64], float (&e)[64], uint32_t a0, uint32_t a1, uint32_t a2, uint32_t a3, uint64_t db) {
  asm volatile("{\n.reg .pred p;\nsetp.ne.b32 p, 1, 0;\n"
               "wgmma.mma_async.sync.aligned.m64n256k16.f32.bf16.bf16 " D128 ", {%128,%129,%130,%131}, %132, p, 1, 1, 1;\n}"
               : R128(d, e) : "r"(a0), "r"(a1), "r"(a2), "r"(a3), "l"(db));
}
template <int N> __device__ __forceinline__ void keep(float (&a)[N]) {
#pragma unroll
  for (int i = 0; i < N; i++) asm volatile("" : "+f"(a[i])::"memory");
}
template <int N> __device__ __forceinline__ void keep(uint32_t (&a)[N]) {
#pragma unroll
  for (int i = 0; i < N; i++) asm volatile("" : "+r"(a[i])::"memory");
}

#define STAMP(idx) do {} while (0)
#define PROF(grp, cond, idx) do {} while (0)

constexpr float SCL2 = 1.4426950408889634f * 0.08838834764831845f;

__device__ __forceinline__ void pack_p(const float (&s)[64], uint32_t (&p)[32]) {
#pragma unroll
  for (int i = 0; i < 32; i++) p[i] = pack_bf(s[2 * i], s[2 * i + 1]);
}

__device__ __forceinline__ void issue_qk(float (&s)[64], uint32_t q0, uint32_t q1, uint32_t kslot) {
  const uint64_t db = make_desc(kslot, 16, 1024), da0 = make_desc(q0, 16, 1024), da1 = make_desc(q1, 16, 1024);
#pragma unroll
  for (int kk = 0; kk < 8; kk++) mma_ss<0>(s, (kk < 4 ? da0 : da1) + (kk & 3) * 2, db + (kk >> 2) * 1024 + (kk & 3) * 2, kk != 0);
}
__device__ __forceinline__ void issue_pv(float (&o)[64], uint32_t (&p)[32], uint32_t vslot, int acc) {
  uint64_t db = make_desc(vslot, 16384, 1024);
#pragma unroll
  for (int kk = 0; kk < 8; kk++)
    mma_rs<1>(o, p[4 * kk], p[4 * kk + 1], p[4 * kk + 2], p[4 * kk + 3], db + kk * 128, kk == 0 ? acc : 1);
}

template <int H>
__device__ __forceinline__ void store_chunk(const float (&a)[64], uint32_t addr) {
#pragma unroll
  for (int i = 8 * H; i < 8 * H + 8; i += 2)
    stmatrix4(addr ^ ((i & 7) << 4), pack_bf(a[4 * i], a[4 * i + 1]), pack_bf(a[4 * i + 2], a[4 * i + 3]),
              pack_bf(a[4 * i + 4], a[4 * i + 5]), pack_bf(a[4 * i + 6], a[4 * i + 7]));
}
template <int H>
__device__ __forceinline__ void store_chunk(const float (&a)[64], float i0, float i1, uint32_t addr) {
#pragma unroll
  for (int i = 8 * H; i < 8 * H + 8; i += 2)
    stmatrix4(addr ^ ((i & 7) << 4), pack_bf(a[4 * i] * i0, a[4 * i + 1] * i0), pack_bf(a[4 * i + 2] * i1, a[4 * i + 3] * i1),
              pack_bf(a[4 * i + 4] * i0, a[4 * i + 5] * i0), pack_bf(a[4 * i + 6] * i1, a[4 * i + 7] * i1));
}
__device__ __forceinline__ float inv_quad_sum(float l) {
  l += __shfl_xor_sync(0xffffffffu, l, 1);
  l += __shfl_xor_sync(0xffffffffu, l, 2);
  return rcp(l);
}

__device__ __forceinline__ void ln_scalars(float mean, float var, float& mb, float& sd) {
  mb = rbf(mean);
  float r; asm("sqrt.approx.ftz.f32 %0, %1;" : "=f"(r) : "f"(rbf(rbf(var) + 1e-5f)));
  sd = rbf(r);
}

__global__ void __cluster_dims__(2, 1, 1) __launch_bounds__(384, 1) fused_kernel(const __grid_constant__ Maps maps, const Ptrs P) {
  extern __shared__ __align__(1024) uint8_t smem_raw[];
  const uint32_t base = smem_u32(smem_raw);
  const int tid = threadIdx.x, lane = tid & 31;
  const int warp = __shfl_sync(0xffffffffu, tid >> 5, 0);
  const int b = blockIdx.x;
  PROF(31, tid == 0, 0);

  if (b >= NMAIN) {
    float* sc = reinterpret_cast<float*>(smem_raw);
    float* red = sc + DM;
    for (int k = tid; k < DM; k += 384) sc[k] = rbf(silu_f(__bfloat162float(P.c[k])));
    __syncthreads();
    if (tid < 256) {
      const int col = 2048 + (b - NMAIN) * 1024 + (tid & 127) * 8, r0 = (tid >> 7) * 512;
      float acc[8];
#pragma unroll
      for (int e = 0; e < 8; e++) acc[e] = 0.f;
#pragma unroll 1
      for (int r = r0; r < r0 + 512; r += HU) {
        uint4 w[HU];
#pragma unroll
        for (int u = 0; u < HU; u++) w[u] = ldg_stream4(P.w_mod + (size_t)(r + u) * NMOD + col);
#pragma unroll
        for (int u = 0; u < HU; u++) {
          float s = sc[r + u];
          acc[0] += s * bf_lo(w[u].x); acc[1] += s * bf_hi(w[u].x); acc[2] += s * bf_lo(w[u].y); acc[3] += s * bf_hi(w[u].y);
          acc[4] += s * bf_lo(w[u].z); acc[5] += s * bf_hi(w[u].z); acc[6] += s * bf_lo(w[u].w); acc[7] += s * bf_hi(w[u].w);
        }
      }
      if (tid >= 128) {
#pragma unroll
        for (int e = 0; e < 8; e++) red[(tid & 127) * 8 + e] = acc[e];
      }
      const uint32_t tag = ld_relaxed(&g_epoch) % 3 + 1;
      bar_sync(1, 256);
      if (tid < 128) {
        uint32_t o[8];
#pragma unroll
        for (int e = 0; e < 8; e++) o[e] = __float_as_uint(rbf(acc[e] + red[tid * 8 + e])) | tag;
        st_relaxed4(g_mod + col, o[0], o[1], o[2], o[3]);
        st_relaxed4(g_mod + col + 4, o[4], o[5], o[6], o[7]);
        const uint4 wr = ldg_nc4(P.w_r + tid * 8);
        const uint32_t wv[4] = {wr.x, wr.y, wr.z, wr.w};
        float dsum = 0.f;
#pragma unroll
        for (int e = 0; e < 8; e++) {
          const float m = bf_hi(o[e]);
          dsum += (b == NMAIN + 2 ? rbf(1.f + m) : m) * ((e & 1) ? bf_hi(wv[e >> 1]) : bf_lo(wv[e >> 1]));
        }
#pragma unroll
        for (int k = 16; k > 0; k >>= 1) dsum += __shfl_xor_sync(0xffffffffu, dsum, k);
        if (lane == 0) st_relaxed(g_mod + (b - NMAIN) * 4 + warp, tagf(dsum, tag));
      }
    }
    PROF(2, tid == 0, 1);
    return;
  }

  const int rank = b & 1;
  const int rb = ((b >> 4) << 1) | rank, cj = (b >> 1) & 7;
  const uint32_t bfull = base + OFF_BAR, bempty = bfull + NSLOT * 8;
  const uint32_t gfull = bempty + NSLOT * 8, gempty = gfull + 32;
  const uint32_t bar_ofull = gempty + 32;
  const uint32_t bar_ofree = bar_ofull + 16;
  const uint32_t bar_par = bar_ofree + 32;
  const uint32_t bar_mod = bar_par + 8;
  const uint32_t bar_pread = bar_mod + 8;
  const uint32_t bar_xres = bar_pread + 8;
  const uint32_t bar_ring = bar_xres + 8;
  const uint32_t bar_box = bar_ring + 24;
  const uint32_t bar_go = bar_box + 96;
  const uint32_t bar_go2 = bar_go + 16;
  const uint32_t bar_cnt = bar_go + 24;
  const uint32_t xfull = bar_go + 32, xempty = xfull + 32;
  const uint32_t bar_hw = xempty + 32, bar_hx = bar_hw + 8;
  const uint32_t bar_hpub = bar_hx + 16;
  const uint32_t bar_win = bar_hpub + 8;
  const uint32_t bar_rx = bar_win + 8;
  const uint32_t bar_sel = bar_rx + 8;
  const uint32_t bar_gate = bar_sel + 8;
  const uint32_t bar_rel = bar_gate + 8;
  const uint32_t bar_res = bar_go + 8;
  const uint32_t stage = base + OFF_STAGE, par = base + OFF_PAR;

  if (warp == 8 && elect_one()) {
    for (int s = 0; s < NSLOT; s++) { mbar_init(bfull + s * 8, 1); mbar_init(bempty + s * 8, 16); }
    for (int s = 0; s < 4; s++) { mbar_init(gfull + s * 8, 1); mbar_init(gempty + s * 8, 16); mbar_init(xfull + s * 8, 1); mbar_init(xempty + s * 8, 8); mbar_init(bar_ofree + s * 8, 1); }
    mbar_init(bar_ofull, 128); mbar_init(bar_ofull + 8, 128);
    mbar_init(bar_par, 64); mbar_init(bar_mod, 256); mbar_init(bar_pread, 8); mbar_init(bar_xres, 1);
    mbar_init(bar_ring, 8); mbar_init(bar_ring + 8, 8); mbar_init(bar_ring + 16, 8);
    mbar_init(bar_go, 1); mbar_init(bar_go2, 1); mbar_init(bar_cnt, 1); mbar_init(bar_hpub, 8); mbar_init(bar_res, 1); mbar_init(bar_win, 1); mbar_init(bar_rx, 1); mbar_init(bar_sel, 64); mbar_init(bar_gate, 8); mbar_init(bar_rel, 8);
    for (int s = 0; s < 12; s++) mbar_init(bar_box + s * 8, 1);
    asm volatile("fence.mbarrier_init.release.cluster;" ::: "memory");
    prefetch_map(&maps.x); prefetch_map(&maps.wq); prefetch_map(&maps.k); prefetch_map(&maps.v);
  }
  if (warp == 9 && elect_one()) {
    mbar_init(bar_hw, 1); mbar_init(bar_hx, 1); mbar_init(bar_hx + 8, 1);
    asm volatile("fence.mbarrier_init.release.cluster;" ::: "memory");
    mbar_expect_tx(bar_hw, 32768);
    mbar_expect_tx(bar_hx, 16384);
    mbar_expect_tx(bar_hx + 8, 16384);
    const __nv_bfloat16* xs = P.x + (size_t)(rb * 128 + cj * 16) * DM;
    bulk_load(base + 2 * GST_BYTES, xs, 16384, bar_hx);
    tma2d(stage, &maps.wm, (b >> 1) * 32, rank * 512, bar_hw);
    tma2d(stage + 16384, &maps.wm, (b >> 1) * 32, rank * 512 + 256, bar_hw);
    bulk_load(base + 3 * GST_BYTES, xs + 8 * DM, 16384, bar_hx + 8);
  }
  cluster_arrive();

  if (warp >= 8) {
    asm volatile("setmaxnreg.dec.sync.aligned.u32 40;");
    if (warp < 10) bar_arrive(1, 320);
    const uint32_t epoch = ld_relaxed(&g_epoch);
    cluster_wait();
    if (warp == 8) {
      const int kvrow = (cj >> 1) * SK + (SK - WIN);
      int wch = cj * 8 + rank * 2;
#pragma unroll 1
      for (int ps = 0; ps < 3; ps++) {
        const CUtensorMap* mw = ps == 2 ? &maps.wo : &maps.wq;
        const uint32_t xt = ps == 1 ? XT1 : XT2, wt = ps == 0 ? WT0 : (ps == 1 ? WT1 : WT2);
        const int nst = ps == 2 ? 32 : 16;
        if (ps) {
          mbar_wait(bar_ofree + (ps - 1) * 16, 0);
          fence_async();
        }
#pragma unroll 1
        for (int i = 0; i < nst; i++) {
          const uint32_t bf = gfull + (i & 3) * 8;
          const int kt = ps == 2 ? (((cj & 1) * 4 + ((i >> 1) & 3)) * 4 + (i >> 3)) * 2 + (i & 1) : (i + (ps ? 0 : b & 14)) & 15;
          const uint32_t wd = base + unit_of(wt, i & 3) + rank * UNIT, xd = base + unit_of(xt, i & 3);
          const uint8_t* xs = g_act + (uint32_t)(rb * 80 + (ps - 1) * 16 + kt) * UNIT;
          if (ps == 0 && i == HD) mbar_wait(bar_mod, 0);
          if (ps && i && i < 4) mbar_wait(bempty + (i == 3 ? 3 : i - 1) * 8, 1);
          mbar_wait(gempty + (i & 3) * 8, ((i >> 2) & 1) ^ 1);
          if (elect_one()) {
            mbar_expect_tx(bf, ps ? GST_BYTES : 2 * UNIT);
            tma3d_mc<true>(wd, mw, 0, (i == 31 ? kt ^ (rank * 32) : kt) * 64, i == 31 ? cj * 2 : wch, bf);
          }
          if (ps) {
            if (i == 16) mbar_wait(bar_cnt, 0);
            if (i == 2) mbar_wait(bempty + 16, 1);
            if (elect_one()) {
              if (i == 31) bulk_load(xd, xs, UNIT, bf); else bulk_load_stream(xd, xs, UNIT, bf);
              mbar_arrive_pred(bar_go, i == GOST - 1);
              mbar_arrive_pred(bar_go2, ps * 16 + i == PG0);
              mbar_arrive_pred(bar_res, ((1u << RES0 | 1u << RES1) >> i) & 1);
              if (ps == 2 && b < NFFN && i >= PD0 && i < PD0 + 16)
                asm volatile("cp.async.bulk.prefetch.L2.global [%0], 4096;" ::"l"(P.w_down + (size_t)b * 32768 + (i - PD0) * 2048) : "memory");
            }
          }
        }
        if (ps == 2) break;
        wch = ps ? ((wch >> 3) ^ rank) * 2 : wch + 4;
#pragma unroll 1
        for (int u = 0; u < 16; u++) {
          const bool isk = (u == 0) || ((u & 1) && u < 15);
          const int blk = (isk ? (u + 1) >> 1 : (u == 15 ? 7 : (u >> 1) - 1)) & 3;
          const uint32_t sl = base + unit_of(ps ? AT1 : AT0, u & 3) + rank * UNIT, bf = bfull + (u & 3) * 8;
          if (u < 4) mbar_wait(gempty + ((u + 1) >> 1) * 8, 1);
          mbar_wait(bempty + (u & 3) * 8, ((u >> 2) & 1) ^ 1);
          if (elect_one()) {
            mbar_expect_tx(bf, SLOT_BYTES);
            tma3d_mc<false>(sl, isk ? &maps.k : &maps.v, 0, kvrow + blk * 128, rank, bf);
            if (ps && u >= PF2T && u < PF2T + 2 * PF2 && !((u - PF2T) & 1))
              tma3d_prefetch(&maps.wo, 0, ((((cj & 1) * 4 + (b >> 5)) * 4 + ((u - PF2T) >> 1)) * 2 + ((b >> 4) & 1)) * 64, (cj ^ rank) * 2);
          }
        }
      }
      if (elect_one()) mbar_expect_tx(bar_rx, UNIT);
      mbar_wait(bar_rel, 0);
      if (elect_one()) {
        bulk_load_stream(base + 8 * UNIT, g_act + (uint32_t)(rb * 80 + 16 + 63 - (cj & 1) * 32) * UNIT, UNIT, bar_rx);
      }
      if (b < NFFN) {
#pragma unroll 1
        for (int u = 0; u < 12; u++) {
          const uint32_t dst = base + unit_of(u < 4 ? FT_G : (u < 8 ? FT_U : FT_D), u & 3);
          if (elect_one()) mbar_expect_tx(bar_box + u * 8, UNIT);
          if (u == FB0 || u == 2 || u == FB2) mbar_wait(bar_ring + (u == FB2 ? 16 : (u + 6) & 8), 0);
          if (u >= FPACE) mbar_wait(bar_box + (u - FPACE) * 8, 0);
          if (elect_one()) {
            if (u < 8) tma2d(dst, u < 4 ? &maps.wg : &maps.wu, b * 32, (u & 3) * 256, bar_box + u * 8);
            else tma3d(dst, &maps.wd, 0, b * 32, (u - 8) * 4, bar_box + u * 8);
          }
        }
      }
    } else if (warp == 9) {
      const uint32_t target = 8 * (epoch + 1);
#pragma unroll 1
      for (int i = 0; i < 16; i++) {
        if (i == HDX) mbar_wait(bar_mod, 0);
        if (i == NRS) {
          wait_counter(&g_cnt_h[rb * 32], target);
          PROF(1, lane == 0, 26);
          fence_async();
        }
        mbar_wait(xempty + (i & 3) * 8, ((i >> 2) & 1) ^ 1);
        if (elect_one()) {
          mbar_expect_tx(xfull + (i & 3) * 8, UNIT);
          if (i < NRS) tma2d(base + (i & 3) * GST_BYTES, &maps.x, ((2 * cj + i) & 15) * 64, rb * 128, xfull + (i & 3) * 8);
          else bulk_load_stream(base + (i & 3) * GST_BYTES, g_act + (uint32_t)(rb * 80 + ((2 * cj + i) & 15)) * UNIT, UNIT, xfull + (i & 3) * 8);
        }
      }
      prefetch_map(&maps.wo);
#pragma unroll 1
      for (int t = 0; t < 4; t++) {
#pragma unroll 1
        for (int w = 0; w < 2; w++) {
          mbar_wait(bar_ofull + w * 8, t & 1);
          uint8_t* dst = g_act + (uint32_t)(rb * 80 + 16 + (cj * 4 + t) * 2) * UNIT + w * 8192;
          if (elect_one()) {
            bulk_store(dst, base + unit_of(QT, 2 * t) + w * 8192, 8192);
            bulk_store(dst + UNIT, base + unit_of(QT, 2 * t + 1) + w * 8192, 8192);
            asm volatile("cp.async.bulk.commit_group;" ::: "memory");
          }
        }
        if (elect_one()) {
          asm volatile("cp.async.bulk.wait_group.read 0;" ::: "memory");
          mbar_arrive(bar_ofree + t * 8);
          asm volatile("cp.async.bulk.wait_group 0;" ::: "memory");
          fence_async();
          red_release(&g_cnt_o[((rb * 4 + t) * 2 + (cj >> 2)) * 32], 2);
        }
        if (t & 1) {
          wait_counter(&g_cnt_o[(rb * 8 + 2 * t - 2 + (cj & 1)) * 32], target);
          wait_counter(&g_cnt_o[(rb * 8 + 2 * t + (cj & 1)) * 32], target);
        }
      }
      wait_counter(&g_cnt_o[(rb * 8 + 7 - (cj & 1)) * 32], target);
      fence_async();
      if (elect_one()) {
        mbar_arrive(bar_cnt);
        PROF(2, true, 27);
        mbar_expect_tx(bar_xres, 32768);
      }
#pragma unroll 1
      for (int u = 0; u < 2; u++) {
        mbar_wait(bar_res, u);
        if (elect_one()) tma2d(base + OFF_RES + u * UNIT, &maps.x, cj * 128 + u * 64, rb * 128, bar_xres);
      }
      const uint32_t tag = epoch % 3 + 1;
      const uint32_t* inbox = g_cand + (lane & 15);
      mbar_wait(bar_ring + 16, 0);
      uint32_t c0 = ld_relaxed(inbox), n = 0;
#define CAND_STEP(cv)                                                                                        \
      {                                                                                                      \
        const bool valid = (cv & 3u) == tag, all = __all_sync(0xffffffffu, valid);                           \
        const uint32_t best = __reduce_max_sync(0xffffffffu, valid ? cv : 0u);                               \
        const uint32_t blk = __ffs(__ballot_sync(0xffffffffu, cv == best)) - 1;                              \
        if (best) sts2(par + PAR_CONST + 56, best, (blk << 7 | (~best >> 2 & 127)) | (all ? 0x1800 : 0x800)); \
        if (all) break;                                                                                      \
        cv = ld_relaxed(inbox);                                                                              \
      }
      while (true) { CAND_STEP(c0) watchdog(n); }
    } else {
      const int t2 = tid - 320;
      if (t2 == 0) {
        mbar_wait(bar_hpub, 0);
        PROF(1, true, 24);
        red_release(&g_cnt_h[rb * 32], 1);
        PROF(1, true, 25);
        prefetch_map(&maps.wg); prefetch_map(&maps.wu); prefetch_map(&maps.wd); prefetch_map(&maps.out);
      }
      __syncwarp();
      if (b < NFFN) {
        mbar_wait(bar_go2, 0);
        const __nv_bfloat16* pg = ((b & 1) ? P.w_up : P.w_gate) + (b >> 1) * 64 + (size_t)t2 * FF;
        const __nv_bfloat16* pd = P.w_down + (size_t)b * 32768 + t2 * 64;
        PROF(2, t2 == 0, 13);
#pragma unroll 1
        for (int i = 0; i < WN; i += WB) {
          uint32_t v[WB];
#pragma unroll
          for (int u = 0; u < WB; u++)
            asm volatile("ld.global.cg.L2::128B.u32 %0, [%1];" : "=r"(v[u]) : "l"(i < 16 ? pg + (size_t)(i + u) * 64 * FF : pd + (i + u - 16) * 4096));
#pragma unroll
          for (int u = 1; u < WB; u++) v[0] ^= v[u];
          sts1(par + PAR_SINK + t2 * 4, v[0]);
        }
        PROF(2, t2 == 0, 14);
      }
      const uint32_t tag = epoch % 3 + 1;
      mbar_wait(bar_go, 0);
      if (warp == 10) {
        const uint32_t* src = g_mod + 2 * DM + cj * 128 + lane * 4;
        const uint2 wr = *reinterpret_cast<const uint2*>(P.w_r + cj * 128 + lane * 4);
        uint4 vga, vsb, vcb, vgb;
        uint32_t n = 0;
        do {
          vga = ld_relaxed4(src); vsb = ld_relaxed4(src + DM); vcb = ld_relaxed4(src + 2 * DM); vgb = ld_relaxed4(src + 3 * DM);
          watchdog(n);
        } while (!(tag_ok(vga, tag) && tag_ok(vsb, tag) && tag_ok(vcb, tag) && tag_ok(vgb, tag)));
        const float c0 = rbf(1.f + bf_hi(vcb.x)), c1 = rbf(1.f + bf_hi(vcb.y)), c2 = rbf(1.f + bf_hi(vcb.z)), c3 = rbf(1.f + bf_hi(vcb.w));
        const float a0 = c0 * bf_lo(wr.x), a1 = c1 * bf_hi(wr.x), a2 = c2 * bf_lo(wr.y), a3 = c3 * bf_hi(wr.y);
        const uint32_t h0 = pack_bf(a0, a1), h1 = pack_bf(a2, a3);
        const uint32_t t1 = par + PAR_T1 + (lane >> 2) * 64 + (lane & 1) * 32 + (lane & 2) * 2;
        sts1(t1, h0); sts1(t1 + 8, pack_bf(a0 - bf_lo(h0), a1 - bf_hi(h0)));
        sts1(t1 + 16, h1); sts1(t1 + 24, pack_bf(a2 - bf_lo(h1), a3 - bf_hi(h1)));
        sts4(par + PAR_T2 + lane * 32, make_uint4(pack_bf(c0, c1), __byte_perm(vsb.x, vsb.y, 0x7632), __byte_perm(vgb.x, vgb.y, 0x7632), __byte_perm(vga.x, vga.y, 0x7632)));
        sts4(par + PAR_T2 + lane * 32 + 16, make_uint4(pack_bf(c2, c3), __byte_perm(vsb.z, vsb.w, 0x7632), __byte_perm(vgb.z, vgb.w, 0x7632), __byte_perm(vga.z, vga.w, 0x7632)));
      } else if (lane < 4) {
        const uint4 g = poll4(lane < 2 ? g_mod + 5 * DM + b * 8 + lane * 4 : g_mod + 16 - lane * 4, tag);
        sts1(par + PAR_CONST + 60, 0);
        if (lane < 2) sts4(par + PAR_CONST + 16 + lane * 16, g);
        else sts2(par + PAR_CONST + (lane - 2) * 8, __float_as_uint(untag_sum(g.x, g.y) + untag_sum(g.z, g.w)), epoch);
      }
      __syncwarp();
#pragma unroll 4
      for (int q = XR; q < XE; q++) st_b128(g_xch + ((size_t)b * 8 * 256 + q * 64 + t2) * 4, (epoch & 1) << 16, 0, 0, 0);
      for (int q = 0; q < 2; q++) st_relaxed4(g_stats + ((size_t)cj * SEQ + rb * 128 + q * 64 + t2) * 4, 0, 0, 0, 0);
      if (b < NFFN)
        for (int q = 0; q < 4; q++) st_relaxed4(g_ypart + ((size_t)(q * 32 + (t2 >> 1)) * NFFN + b) * 8 + (t2 & 1) * 4, 0, 0, 0, 0);
      st_relaxed4(g_row + rb * 2 * DM + (t2 >> 5) * DM + cj * 128 + (t2 & 31) * 4, 0, 0, 0, 0);
      __threadfence();
      mbar_arrive(bar_par);
      mbar_wait(bar_gate, 0);
      uint32_t have = 0, n = 0;
      while (true) {
        const uint32_t st = lds1(par + PAR_CONST + 60) >> 7;
        if ((st & 31) != have) {
          const uint32_t* hsrc = g_row + (st & 15) * 2 * DM + t2 * 4;
          uint4 hv[4];
          bool ok = true;
#pragma unroll
          for (int i = 0; i < 4; i++) hv[i] = ld_pairs(hsrc + i * 256);
#pragma unroll
          for (int i = 0; i < 4; i++) {
            sts2(base + ((FT_G >> i * 4) & 15) * UNIT + (warp & 1) * 8192 + 256 + lane * 8, hv[i].x, hv[i].z);
            ok = ok && hv[i].y == tag && hv[i].w == tag;
          }
          have = __all_sync(0xffffffffu, ok) ? st & 31 : 0;
        }
        if ((st ^ have) == 32) break;
        watchdog(n);
      }
      mbar_arrive(bar_sel);
    }
    __syncwarp();
    cluster_arrive();
    {
      const uint32_t tag = epoch % 3 + 1, t3 = tid - 256;
      mbar_wait(bar_win, 0);
      uint2 win = lds2(par + PAR_CONST + 56);
      win.y &= 0x7ff;
      const uint32_t* fsrc = g_row + (win.y >> 7) * 2 * DM + (b >> 1) * 16 + (t3 & 3) * 4 + (b & 1) * 2;
      const uint32_t* ysrc = g_ypart + (size_t)b * NFFN * 8 + min(t3, NFFN - 1) * 4;
      uint2 fh = ld_pair(fsrc), fx = ld_pair(fsrc + DM);
      if (PSL) __nanosleep(PSL);
      uint4 ya = ld_relaxed4(ysrc), yb = ld_relaxed4(ysrc + NFFN * 4);
      const float rwin = __uint_as_float(((int)win.x < 0 ? win.x & 0x7fffffffu : ~win.x) & ~0x1ffu);
      const float rs = rbf(rcp(1.f + __expf(-rbf(rwin))));
      uint32_t n = 0;
      while (fh.y != tag || fx.y != tag) { fh = ld_pair(fsrc); fx = ld_pair(fsrc + DM); watchdog(n); }
      while (!(tag_ok(ya, tag) && tag_ok(yb, tag))) {
        if (!tag_ok(ya, tag)) ya = ld_relaxed4(ysrc);
        if (!tag_ok(yb, tag)) yb = ld_relaxed4(ysrc + NFFN * 4);
        watchdog(n);
      }
      __syncwarp();
      PROF(8, t3 == 0, 5);
      float y0 = untag_sum(ya.x, yb.x), y1 = untag_sum(ya.y, yb.y), y2 = untag_sum(ya.z, yb.z), y3 = untag_sum(ya.w, yb.w);
      const bool u1 = lane & 2, u2 = lane & 4;
      y0 = (u1 ? y2 : y0) + __shfl_xor_sync(0xffffffffu, u1 ? y0 : y2, 2);
      y1 = (u1 ? y3 : y1) + __shfl_xor_sync(0xffffffffu, u1 ? y1 : y3, 2);
      y0 = (u2 ? y1 : y0) + __shfl_xor_sync(0xffffffffu, u2 ? y0 : y1, 4);
      y0 += __shfl_xor_sync(0xffffffffu, y0, 8);
      if (!(lane & 8)) sts1(par + PAR_RED + 64 + (t3 >> 4) * 32 + ((lane & 1) * 4 + (lane & 2) + ((lane >> 2) & 1)) * 4, __float_as_uint(y0));
      bar_sync(4, 128);
      if (t3 < 4) {
        y0 = 0.f; y1 = 0.f;
#pragma unroll
        for (int w4 = 0; w4 < 7; w4++) {
          const uint2 v = lds2(par + PAR_RED + 64 + w4 * 32 + t3 * 8);
          y0 += __uint_as_float(v.x); y1 += __uint_as_float(v.y);
        }
        const uint2 gv = lds2(par + PAR_CONST + 16 + t3 * 8);
        const uint32_t upd = hmul2(pack_bf(y0, y1), pack_bf(rs, rs));
        *reinterpret_cast<uint32_t*>(P.out + (size_t)win.y * DM + b * 8 + t3 * 2) =
            hadd2(fx.x, hmul2(__byte_perm(gv.x, gv.y, 0x7632), hadd2(fh.x, upd)));
        if (b == 0 && t3 == 0) st_relaxed(&g_epoch, epoch + 1);
      }
      PROF(31, t3 == 0, 36);
    }
    cluster_wait();
  } else {
    const int wg = warp >> 2;

    uint32_t tag;
    {
      uint32_t* const pmod = g_modp + rank * 2 * DM + (b >> 1) * 32 + lane;
      uint32_t* const pln = g_ln1 + (rb * 128 + cj * 16 + warp) * 4;
      const uint32_t cv = ldg_nc1(P.c + rank * 512 + tid * 2);
      const uint32_t epoch = ld_relaxed(&g_epoch);
      if (warp == 0) st_relaxed(pmod, 0);
      if (lane == 0) { st_relaxed2(pln, 0, 0); st_relaxed2(pln + 32, 0, 0); }
      asm volatile("setmaxnreg.inc.sync.aligned.u32 232;");
      sts1(par + tid * 4, pack_bf(silu_f(bf_lo(cv)), silu_f(bf_hi(cv))));
      bar_sync(1, 320);
      tag = epoch % 3 + 1;
#pragma unroll
      for (int part = 0; part < 3; part++) {
        if (part != 1) {
          const uint32_t xa = base + (2 + part / 2) * GST_BYTES + warp * 2048 + lane * 16;
          mbar_wait(bar_hx + part * 4, 0);
          float s0 = 0.f, s1 = 0.f, q0 = 0.f, q1 = 0.f;
#pragma unroll
          for (int q = 0; q < 4; q++) {
            const uint4 xv = lds4(xa + q * 512);
            const uint32_t u[4] = {xv.x, xv.y, xv.z, xv.w};
#pragma unroll
            for (int e = 0; e < 4; e++) { const float lo = bf_lo(u[e]), hi = bf_hi(u[e]); s0 += lo; s1 += hi; q0 += lo * lo; q1 += hi * hi; }
          }
          s0 += s1; q0 += q1;
#pragma unroll
          for (int o = 16; o > 0; o >>= 1) { s0 += __shfl_xor_sync(0xffffffffu, s0, o); q0 += __shfl_xor_sync(0xffffffffu, q0, o); }
          const float mean = s0 * (1.f / DM);
          float mb, sd;
          ln_scalars(mean, fmaxf(q0 * (1.f / DM) - mean * mean, 0.f), mb, sd);
          if (lane == 0) st_relaxed2(pln + part * 16, __float_as_uint(mb) | tag, __float_as_uint(sd) | tag);
          PROF(1, tid == 0 && part == 2, 4);
        } else {
          float acc[8];
#pragma unroll
          for (int e = 0; e < 8; e++) acc[e] = 0.f;
          const uint32_t wa = stage + (tid >> 2) * 64 + (((tid ^ (tid >> 3)) & 3) << 4), sa = par + (tid >> 3) * 4, sh = (tid & 4) ? 0x3244 : 0x1044;
          mbar_wait(bar_hw, 0);
#pragma unroll
          for (int p = 0; p < 8; p++) {
            const uint4 w = lds4(wa + p * 4096);
            const float s = __uint_as_float(__byte_perm(lds1(sa + p * 128), 0, sh));
            acc[0] += s * bf_lo(w.x); acc[1] += s * bf_hi(w.x); acc[2] += s * bf_lo(w.y); acc[3] += s * bf_hi(w.y);
            acc[4] += s * bf_lo(w.z); acc[5] += s * bf_hi(w.z); acc[6] += s * bf_lo(w.w); acc[7] += s * bf_hi(w.w);
          }
#pragma unroll
          for (int e = 0; e < 4; e++) {
            const bool up = lane & 16;
            acc[e] = (up ? acc[e + 4] : acc[e]) + __shfl_xor_sync(0xffffffffu, up ? acc[e] : acc[e + 4], 16);
          }
#pragma unroll
          for (int e = 0; e < 2; e++) {
            const bool up = lane & 8;
            acc[e] = (up ? acc[e + 2] : acc[e]) + __shfl_xor_sync(0xffffffffu, up ? acc[e] : acc[e + 2], 8);
          }
          {
            const bool up = lane & 4;
            acc[0] = (up ? acc[1] : acc[0]) + __shfl_xor_sync(0xffffffffu, up ? acc[0] : acc[1], 4);
          }
          sts1(par + 1024 + warp * 128 + ((lane & 3) * 8 + (lane >> 2)) * 4, __float_as_uint(acc[0]));
          bar_sync(1, 256);
          if (warp == 0) {
            float s = 0.f;
#pragma unroll
            for (int w8 = 0; w8 < 8; w8++) s += __uint_as_float(lds1(par + 1024 + w8 * 128 + lane * 4));
            st_relaxed(pmod, (__float_as_uint(s) & ~3u) | tag);
          }
          PROF(1, tid == 0, 3);
        }
      }
      {
        uint2 s0 = ld_relaxed2(g_ln1 + (rb * 128 + (tid & 127)) * 4);
        uint4 v[4];
#pragma unroll
        for (int q = 0; q < 4; q++) v[q] = ld_relaxed4(g_modp + q * DM + tid * 4);
        {
          uint32_t n = 0;
          while (!(tag_ok(v[0], tag) && tag_ok(v[1], tag) && tag_ok(v[2], tag) && tag_ok(v[3], tag))) {
#pragma unroll
            for (int q = 0; q < 4; q++)
              if (!tag_ok(v[q], tag)) v[q] = ld_relaxed4(g_modp + q * DM + tid * 4);
            if (((s0.x ^ tag) | (s0.y ^ tag)) & 3u) s0 = ld_relaxed2(g_ln1 + (rb * 128 + (tid & 127)) * 4);
            watchdog(n);
          }
        }
        const uint32_t d = stage + (tid >> 2) * 64 + (tid & 1) * 32 + (tid & 2) * 2;
        sts1(d, pack_bf(1.f + rbf(untag_sum(v[1].x, v[3].x)), 1.f + rbf(untag_sum(v[1].y, v[3].y))));
        sts1(d + 16, pack_bf(1.f + rbf(untag_sum(v[1].z, v[3].z)), 1.f + rbf(untag_sum(v[1].w, v[3].w))));
        sts1(d + 8, pack_bf(untag_sum(v[0].x, v[2].x), untag_sum(v[0].y, v[2].y)));
        sts1(d + 24, pack_bf(untag_sum(v[0].z, v[2].z), untag_sum(v[0].w, v[2].w)));
        if (wg == 0) {
          uint32_t n = 0;
          while (((s0.x ^ tag) | (s0.y ^ tag)) & 3u) { s0 = ld_relaxed2(g_ln1 + (rb * 128 + tid) * 4); watchdog(n); }
          uint32_t ih, il;
          split_inv(bf_hi(s0.y), ih, il);
          sts4(stage + 4096 + tid * 16, make_uint4(__byte_perm(s0.x, 0, 0x3232), ih, il, 0));
        }
        mbar_arrive(bar_mod);
      }
      cluster_wait();
      if (wg == 1) bar_arrive(2, 256);
      mbar_wait(bar_mod, 0);
      PROF(1, tid == 0, 2);
    }

    float f0 = 0.f, f1 = 0.f;
    const uint32_t rempty = lane < 2 ? mapa(bempty, lane & 1) : 0;
    constexpr uint32_t GE = NSLOT * 8 + 32;
    float o[64], s[64];
#pragma unroll 1
    for (int ps = 0; ps < 3; ps++) {
      {
        const uint32_t xt = ps == 1 ? XT1 : XT2, wt = ps == 1 ? WT1 : WT2;
        const int nst = ps == 2 ? 28 : 14;
        if (ps == 0) {
          float ga[64], gb[64];
#pragma unroll
          for (int i = 0; i < 64; i++) { ga[i] = 0.f; gb[i] = 0.f; }
          uint32_t a[2][16];
          const uint32_t l = fresh_lane();
          const uint4 r0 = lds4(stage + 4096 + (warp * 16 + (l >> 2)) * 16), r1 = lds4(stage + 4096 + 128 + (warp * 16 + (l >> 2)) * 16);
          auto transform = [&](int i, uint32_t (&f)[16], uint32_t z) {
            const uint32_t ad = base + (i & 3) * GST_BYTES + wg * 8192 + frag_offset(warp) + z;
            mbar_wait(xfull + (i & 3) * 8, i >> 2);
#pragma unroll
            for (int kk = 0; kk < 4; kk++) ldmatrix4(ad ^ (kk * 32), f[4 * kk], f[4 * kk + 1], f[4 * kk + 2], f[4 * kk + 3]);
#pragma unroll
            for (int kk = 0; kk < 4; kk++) {
              const uint4 m = lds4(stage + (l & 3) * 16 + ((2 * cj + i) & 15) * 256 + kk * 64);
              f[4 * kk] = ln_mod(f[4 * kk], r0.x, r0.y, r0.z, m.x, m.z);
              f[4 * kk + 1] = ln_mod(f[4 * kk + 1], r1.x, r1.y, r1.z, m.x, m.z);
              f[4 * kk + 2] = ln_mod(f[4 * kk + 2], r0.x, r0.y, r0.z, m.y, m.w);
              f[4 * kk + 3] = ln_mod(f[4 * kk + 3], r1.x, r1.y, r1.z, m.y, m.w);
            }
            keep(f);
            mbar_arrive_pred(xempty + (i & 3) * 8, l == 0);
          };
          auto publish = [&](int u, uint32_t (&f)[16]) {
            const uint32_t sc = stage + 8192 + wg * 8192;
#pragma unroll
            for (int kk = 0; kk < 4; kk++) stmatrix4((sc + frag_offset(warp)) ^ (kk * 32), f[4 * kk], f[4 * kk + 1], f[4 * kk + 2], f[4 * kk + 3]);
            __syncwarp();
            const uint32_t src = sc + (warp & 3) * 2048 + l * 16;
            uint8_t* dst = g_act + (uint32_t)(rb * 80 + cj * 2 + u) * UNIT + warp * 2048 + l * 16;
#pragma unroll
            for (int p4 = 0; p4 < 4; p4++) stg4(dst + p4 * 512, lds4(src + p4 * 512));
            __syncwarp();
            if (u == 1) mbar_arrive_pred(bar_hpub, l == 0);
          };
          auto multiply = [&](int i, uint32_t (&f)[16]) {
            mbar_wait(gfull + (i & 3) * 8, i >> 2);
            const uint64_t db = make_desc(base + (i & 3) * GST_BYTES + UNIT, 8192, 1024);
            wg_fence();
#pragma unroll
            for (int kk = 0; kk < 4; kk++) mma256_rs(ga, gb, f[4 * kk], f[4 * kk + 1], f[4 * kk + 2], f[4 * kk + 3], db + kk * 128);
            wg_commit();
          };
          transform(0, a[0], 0); publish(0, a[0]); transform(1, a[1], 0); multiply(0, a[0]); publish(1, a[1]);
#pragma unroll
          for (int i = 1; i < NRS; i++) {
            if (i >= 2) {
              uint32_t z = r0.w;
#pragma unroll
              for (int k = 0; k < 16; k += 2) asm volatile("lop3.b32 %0, %1, %2, %0, 0xA8;" : "+r"(z) : "r"(a[i & 1][k]), "r"(a[i & 1][k + 1]));
              transform(i, a[i & 1], z);
            }
            multiply(i, a[i & 1]);
            wg_wait<1>();
            mbar_arrive_cl(rempty, GE + ((i + 3) & 3) * 8);
          }
          mbar_arrive_pred(bar_pread, l == 0);
#pragma unroll 1
          for (int i = NRS; i < 14; i++) {
            mbar_wait(xfull + (i & 3) * 8, (i >> 2) & 1);
            mbar_wait(gfull + (i & 3) * 8, (i >> 2) & 1);
            const uint32_t xa = base + (i & 3) * GST_BYTES;
            const uint64_t da = make_desc(xa + wg * 8192, 16, 1024), db = make_desc(xa + UNIT, 8192, 1024);
            if (i == 13) bar_sync(2 + wg, 256);
            wg_fence();
#pragma unroll
            for (int kk = 0; kk < 4; kk++) mma256_ss(ga, gb, da + kk * 2, db + kk * 128, 1);
            wg_commit();
            if (i == 13) bar_arrive(3 - wg, 256);
            wg_wait<1>();
            uint32_t z = r0.w;
#pragma unroll
            for (int k = 0; k < 16; k += 2) asm volatile("lop3.b32 %0, %1, %2, %0, 0xA8;" : "+r"(z) : "r"(a[1][k]), "r"(a[1][k + 1]));
            mbar_arrive_cl(rempty, GE + ((i + 3) & 3) * 8 + z);
            mbar_arrive_pred(xempty + ((i + 3) & 3) * 8, l == 0 && i != NRS);
          }
          mbar_wait(xfull + 16, 1);
          mbar_wait(xfull + 24, 1);
          wg_wait<0>();
          keep(ga); keep(gb);
#pragma unroll
          for (int i = 0; i < 64; i++) {
            asm volatile("mov.b32 %0, %1;" : "=f"(s[i]) : "f"(ga[i]));
            asm volatile("mov.b32 %0, %1;" : "=f"(o[i]) : "f"(gb[i]));
          }
        } else {
          float ga[64], gb[64];
#pragma unroll
          for (int i = 0; i < 64; i++) {
            asm volatile("mov.b32 %0, %1;" : "=f"(ga[i]) : "f"(s[i]));
            asm volatile("mov.b32 %0, %1;" : "=f"(gb[i]) : "f"(o[i]));
          }
#pragma unroll 1
          for (int i = 0; i < nst; i++) {
            mbar_wait(gfull + (i & 3) * 8, (i >> 2) & 1);
            const uint64_t da = make_desc(base + unit_of(xt, i & 3) + wg * 8192, 16, 1024), db = make_desc(base + unit_of(wt, i & 3), 8192, 1024);
            if (i == nst - 1) bar_sync(2 + wg, 256);
            wg_fence();
#pragma unroll
            for (int kk = 0; kk < 4; kk++) mma256_ss(ga, gb, da + kk * 2, db + kk * 128, kk ? 1 : i);
            wg_commit();
            if (i == nst - 1) bar_arrive(3 - wg, 256);
            wg_wait<1>();
            mbar_arrive_cl(rempty, GE + ((i + 3) & 3) * 8, i != 0);
            PROF(4, tid == 0 && (i & 3) == 0, 40 + (ps - 1) * 4 + i / 4);
          }
          wg_wait<0>();
          keep(ga); keep(gb);
#pragma unroll
          for (int i = 0; i < 64; i++) {
            asm volatile("mov.b32 %0, %1;" : "=f"(s[i]) : "f"(ga[i]));
            asm volatile("mov.b32 %0, %1;" : "=f"(o[i]) : "f"(gb[i]));
          }
        }
        mbar_arrive_cl(rempty, GE + (ps == 2 ? 24 : 8));
        if (ps == 2) break;
      }
      const uint32_t qw = base + wg * 8192, qt = QT >> (16 * ps), at = ps ? AT1 : AT0;
      {
        const uint32_t wt = ps ? WT1 : WT0;
        const uint64_t da0 = make_desc(qw + unit_of(qt, 2), 16, 1024), da1 = make_desc(qw + unit_of(qt, 3), 16, 1024);
        const uint64_t db0 = make_desc(base + unit_of(wt, 2), 8192, 1024), db1 = make_desc(base + unit_of(wt, 3), 8192, 1024);
        mbar_wait(gfull + 16, 1);
        mbar_wait(gfull + 24, 1);
        bar_sync(2 + wg, 256);
        wg_fence();
#pragma unroll
        for (int kk = 0; kk < 8; kk++) mma_ss<1>(s, (kk < 4 ? da0 : da1) + (kk & 3) * 2, (kk < 4 ? db0 : db1) + (kk & 3) * 128, 1);
        wg_commit();
        bar_arrive(3 - wg, 256);
        mbar_wait(ps == 0 ? bar_pread : bar_ofree + 8, 0);
        mbar_wait(bfull, 0);
        wg_wait<0>();
        keep(s);
        PROF(2, tid == 0, 8 + ps * 8);
        store_chunk<0>(s, qw + unit_of(qt, 0) + frag_offset(warp));
        store_chunk<1>(s, qw + unit_of(qt, 1) + frag_offset(warp));
        fence_async_smem();
        bar_sync(2 + wg, 256);
        wg_fence();
        issue_qk(s, qw + unit_of(qt, 0), qw + unit_of(qt, 1), base + unit_of(at, 0));
        wg_commit();
#pragma unroll
        for (int kk = 0; kk < 8; kk++) mma_ss<1>(o, (kk < 4 ? da0 : da1) + (kk & 3) * 2, (kk < 4 ? db0 : db1) + UNIT / 16 + (kk & 3) * 128, 1);
        wg_commit();
        bar_arrive(3 - wg, 256);
        wg_wait<1>();
        keep(s);
        mbar_arrive_cl(rempty, 0);
      }
      PROF(4, tid == 0 && ps == 1, 61);
      float l0 = 0.25f, l1 = 0.25f;
      auto step = [&](auto odd_c, const int j, uint32_t (&pw)[32], uint32_t (&pr)[32]) {
        constexpr bool ODD = decltype(odd_c)::value;
        const bool first = !ODD && (j & 2) == 0, last = ODD && j == 7;
        const uint32_t ph = (j >> 1) & 1;
        float i0, i1, a0, a1;
        if (first) { i0 = inv_quad_sum(l0); i1 = inv_quad_sum(l1); l0 = 0.f; l1 = 0.f; }
        bool redo = !ODD && (j | ps) == 0, again = false;
        while (true) {
          if (redo) {
            float m0 = fmaxf(s[0], s[1]), m1 = fmaxf(s[2], s[3]);
#pragma unroll
            for (int i = 1; i < 16; i++) { m0 = fmaxf(m0, fmaxf(s[4 * i], s[4 * i + 1])); m1 = fmaxf(m1, fmaxf(s[4 * i + 2], s[4 * i + 3])); }
            m0 = fmaxf(m0, __shfl_xor_sync(0xffffffffu, m0, 1)); m1 = fmaxf(m1, __shfl_xor_sync(0xffffffffu, m1, 1));
            m0 = fmaxf(m0, __shfl_xor_sync(0xffffffffu, m0, 2)); m1 = fmaxf(m1, __shfl_xor_sync(0xffffffffu, m1, 2));
            m0 *= SCL2; m1 *= SCL2;
            if (!first) {
              m0 = fmaxf(m0, f0); m1 = fmaxf(m1, f1);
              const float c0 = ex2(f0 - m0), c1 = ex2(f1 - m1);
              l0 *= c0; l1 *= c1;
              wg_wait<0>();
              keep(o);
#pragma unroll
              for (int i = 0; i < 16; i++) { o[4 * i] *= c0; o[4 * i + 1] *= c0; o[4 * i + 2] *= c1; o[4 * i + 3] *= c1; }
            }
            f0 = m0; f1 = m1;
          }
          float b0 = 0.f, b1 = 0.f;
          a0 = 0.f; a1 = 0.f;
#pragma unroll
          for (int i = 0; i < 16; i++) {
            const float e0 = ex2(fmaf(s[4 * i], SCL2, -f0)), e1 = ex2(fmaf(s[4 * i + 1], SCL2, -f0));
            const float e2 = ex2(fmaf(s[4 * i + 2], SCL2, -f1)), e3 = ex2(fmaf(s[4 * i + 3], SCL2, -f1));
            a0 += e0; b0 += e1; a1 += e2; b1 += e3;
            pw[2 * i] = pack_bf(e0, e1); pw[2 * i + 1] = pack_bf(e2, e3);
            if (i == VREL) {
#pragma unroll
              for (int k = 0; k < 2 * VREL + 2; k++) asm volatile("" : "+r"(pw[k])::"memory");
              mbar_wait(bfull + (ODD ? 24 : 8), ph);
              wg_wait<0>();
              mbar_arrive_cl(rempty, ODD ? 16 : (j ? 0 : GE + 16), !again);
              if (!ODD) mbar_arrive_cl(rempty, GE + 24, !again && j == 0);
#pragma unroll
              for (int k = 4 * VREL + 4; k < 64; k++) asm volatile("" : "+f"(s[k])::"memory");
            }
          }
          a0 += b0; a1 += b1;
          if (redo) break;
          redo = __any_sync(0xffffffffu, !(a0 + a1 < 0x1p70f));
          if (first) {
            uint32_t m0 = __ballot_sync(0xffffffffu, a0 > 0x1p-50f), m1 = __ballot_sync(0xffffffffu, a1 > 0x1p-50f);
            m0 |= m0 >> 1; m1 |= m1 >> 1; m0 |= m0 >> 2; m1 |= m1 >> 2;
            redo = redo || (m0 & m1 & 0x11111111u) != 0x11111111u;
          }
          if (!redo) break;
          again = true;
        }
        l0 += a0; l1 += a1;
        keep(pw);
        keep(o);
        const uint32_t qo = qt >> (j ? 0 : 8);
        if (first) store_chunk<0>(o, i0, i1, qw + unit_of(qo, 0) + frag_offset(warp));
        keep(o);
        bar_sync(2 + wg, 256);
        if (!last) {
          const uint32_t qn = qt >> (j >= 3 ? 8 : 0);
          wg_fence();
          issue_qk(s, qw + unit_of(qn, 0), qw + unit_of(qn, 1), base + unit_of(at, ODD ? 3 : 1));
          wg_commit();
          mbar_wait(bfull + (ODD ? 0 : 16), ODD ? ph ^ 1 : ph);
        }
        if (first) { store_chunk<1>(o, i0, i1, qw + unit_of(qo, 1) + frag_offset(warp)); keep(o); }
        wg_fence();
        issue_pv(o, pw, base + unit_of(at, ODD ? (last ? 3 : 0) : 2), !first);
        wg_commit();
        bar_arrive(3 - wg, 256);
        if (first) { fence_async_smem(); mbar_arrive_pred(bar_ofull + wg * 8, j); PROF(2, tid == 0 && j, 9 + ps * 8); }
        wg_wait<1>();
        keep(s);
        mbar_arrive_cl(rempty, ODD ? 24 : 8, !last);
        PROF(4, tid == 0 && ps == 1, 51 + j);
      };
      uint32_t pa[32], pb[32];
#pragma unroll 1
      for (int j = 0; j < 8; j += 2) {
        step(std::false_type{}, j, pa, pb);
        step(std::true_type{}, j + 1, pb, pa);
      }
      {
        const float i0 = inv_quad_sum(l0), i1 = inv_quad_sum(l1);
        wg_wait<0>();
        keep(o);
        mbar_arrive_cl(rempty, 24);
        store_chunk<0>(o, i0, i1, qw + unit_of(qt, 2) + frag_offset(warp));
        store_chunk<1>(o, i0, i1, qw + unit_of(qt, 3) + frag_offset(warp));
        fence_async_smem();
        mbar_arrive(bar_ofull + wg * 8);
      }
      PROF(2, tid == 0, 10 + ps * 8);
    }

    const int ln = fresh_lane(), g = ln >> 2, tq = ln & 3, ct = warp * 32 + ln;
    const bool lane0 = ln == 0;
    const int lrow0 = warp * 16 + g;
    const int grow0 = rb * 128 + lrow0;
    const uint32_t res = base + OFF_RES, trow = res + wg * 8192 + frag_offset(warp);
    uint32_t xr[32];
    uint4 sv[4], own;
    uint32_t* sp[4];
#pragma unroll
    for (int k = 0; k < 4; k++) sp[k] = g_stats + ((((tq >> 1) * 4 + k) ^ cj) * SEQ + grow0 + (tq & 1) * 8) * 4;
    {
      const uint64_t da = make_desc(base + wg * 8192, 16, 1024), db = make_desc(base, 8192, 1024);
      constexpr int U = UNIT / 16;
#define HALF_STAGE(acc, xu, wu) _Pragma("unroll") for (int kk = 0; kk < 4; kk++) mma_ss<1>(acc, da + (xu) * U + kk * 2, db + (wu) * U + kk * 128, 1)
      PROF(10, ct == PT, 19); STAMP(0);
      cluster_arrive();
      mbar_wait(gfull, 1);
      mbar_wait(gfull + 8, 1);
      bar_sync(2 + wg, 256);
      wg_fence();
      HALF_STAGE(o, 6, 8);
      HALF_STAGE(o, 9, 11);
      wg_commit();
      STAMP(16);
      mbar_wait(gfull + 16, 1);
      STAMP(17);
      wg_fence();
      HALF_STAGE(o, 12, 1);
      wg_commit();
      bar_arrive(3 - wg, 256);
      mbar_wait(bar_par, 0);
      uint32_t* xo = g_xch + ((size_t)b * 8 * 256 + ct) * 4;
      const uint32_t* xi = g_xch + ((size_t)(b ^ 2) * 8 * 256 + ct) * 4;
      const uint32_t par1 = (~lds1(par + PAR_CONST + 4) & 1) << 16;
      uint32_t ga[16];
      uint4 bw[8];
#define LOAD_PAR _Pragma("unroll") for (int i = 0; i < 8; i++) {                                                               \
        ga[2 * i] = lds1(par + PAR_T2 + i * 128 + tq * 16 + 12); ga[2 * i + 1] = lds1(par + PAR_T2 + i * 128 + 64 + tq * 16 + 12); \
        bw[i] = lds4(par + PAR_T1 + i * 64 + tq * 16);                                                                          \
        if (!(g & 1)) { bw[i].x = 0x3f803f80u; bw[i].y = 0x3f803f80u; }                                                         \
      }
      if (PPOS == 0) LOAD_PAR
      wg_wait<1>();
      mbar_arrive_pred(bar_rel, lane0);
      wg_wait<0>();
      keep(o);
      mbar_arrive_pred(bar_ring, lane0);
      PROF(8, ct == PT, 20); STAMP(1);
#define SEND(i) st_b128(xo + (i) * 1024, (pack_bf(o[8 * (i)], o[8 * (i) + 1]) & ~0x10000u) | par1, pack_bf(o[8 * (i) + 2], o[8 * (i) + 3]), \
                        pack_bf(o[8 * (i) + 4], o[8 * (i) + 5]), pack_bf(o[8 * (i) + 6], o[8 * (i) + 7]))
#pragma unroll
      for (int i = 0; i < NS1; i++) SEND(i);
      PROF(8, ct == PT, 21); STAMP(2);
      bar_sync(2 + wg, 256);
      wg_fence();
      HALF_STAGE(s, 6, 7);
      HALF_STAGE(s, 9, 10);
      HALF_STAGE(s, 12, 0);
      wg_commit();
      bar_arrive(3 - wg, 256);
      STAMP(18);
      mbar_wait(gfull + 24, 1);
#pragma unroll
      for (int i = NS1; i < 8; i++) SEND(i);
      uint4 v[8];
#pragma unroll
      for (int i = 0; i < 4; i++) v[i] = ld_b128(xi + i * 1024);
      if (PPOS == 1) LOAD_PAR
      STAMP(19);
      mbar_wait(bar_xres, 0);
      wg_wait<0>();
      mbar_arrive_pred(bar_ring + 8, lane0);
      bar_sync(2 + wg, 256);
      STAMP(20);
#pragma unroll
      for (int i = 4; i < 8; i++) v[i] = ld_b128(xi + i * 1024);
      mbar_wait(bar_xres, 0);
      wg_fence();
      HALF_STAGE(s, 13, 2);
      wg_commit();
      mbar_wait(bar_rx, 0);
      wg_fence();
      HALF_STAGE(s, 8, 3);
      wg_commit();
      bar_arrive(3 - wg, 256);
      STAMP(21);
      wg_wait<0>();
      keep(s);
      mbar_arrive_pred(bar_ring + 16, lane0);
      PROF(10, ct == PT, 23); STAMP(4);
#pragma unroll
      for (int i = 0; i < 16; i += 2) ldmatrix4((trow ^ ((i & 7) << 4)) + (i >> 3) * 16384, xr[2 * i], xr[2 * i + 1], xr[2 * i + 2], xr[2 * i + 3]);
      if (PPOS == 2) LOAD_PAR
      uint32_t pk[32];
      pack_p(s, pk);
      keep(pk);
      {
        uint32_t n = 0;
        bool ok;
        do {
          ok = true;
#pragma unroll
          for (int i = 0; i < 8; i++)
            if ((v[i].x & 0x10000u) != par1) { v[i] = ld_b128(xi + i * 1024); ok = false; }
          watchdog(n);
        } while (!ok);
      }
      __syncwarp();
      PROF(8, ct == PT, 22); STAMP(3);
#pragma unroll
      for (int k = 0; k < 4; k++) sv[k] = ESV ? ld_b128(sp[k]) : make_uint4(0, 0, 0, 0);
      float ds[4] = {0.f, 0.f, 0.f, 0.f}, dl[4] = {0.f, 0.f, 0.f, 0.f}, q0[4] = {0.f, 0.f, 0.f, 0.f}, q1[4] = {0.f, 0.f, 0.f, 0.f};
#pragma unroll
      for (int i = 0; i < 8; i++) {
        const uint32_t u0 = hfma2(ga[2 * i], hadd2(pk[4 * i], v[i].x & ~0x10000u), xr[4 * i]);
        const uint32_t u1 = hfma2(ga[2 * i], hadd2(pk[4 * i + 1], v[i].y), xr[4 * i + 1]);
        const uint32_t u2 = hfma2(ga[2 * i + 1], hadd2(pk[4 * i + 2], v[i].z), xr[4 * i + 2]);
        const uint32_t u3 = hfma2(ga[2 * i + 1], hadd2(pk[4 * i + 3], v[i].w), xr[4 * i + 3]);
        xr[4 * i] = u0; xr[4 * i + 1] = u1; xr[4 * i + 2] = u2; xr[4 * i + 3] = u3;
        mma16816(ds, u0, u1, u2, u3, bw[i].x, bw[i].y);
        mma16816(dl, u0, u1, u2, u3, bw[i].z, bw[i].w);
        mma16816(q0, u0, u1, u2, u3, u0, u2);
        mma16816(q1, u0, u1, u2, u3, u1, u3);
      }
      const float sqa = __shfl_sync(0xffffffffu, (g & 1) ? q0[1] : q0[0], g * 4 + (g >> 1));
      const float sqb = __shfl_sync(0xffffffffu, (g & 1) ? q1[3] : q1[2], g * 4 + (g >> 1));
      own = (tq & 1) ? make_uint4(__float_as_uint(ds[2]), __float_as_uint(sqb), __float_as_uint(ds[3] + dl[3]), tag)
                                 : make_uint4(__float_as_uint(ds[0]), __float_as_uint(sqa), __float_as_uint(ds[1] + dl[1]), tag);
      if (tq < 2) st_b128(sp[0], own.x, own.y, own.z, own.w);
    }
    PROF(8, ct == PT, 29); STAMP(5);
    uint32_t mm, ih, il;
    float rbest;
    uint32_t wf[128];
    const uint32_t frow = (ln & 7) + (ln >> 4) * 8;
    const uint32_t wfo = base + (warp & 1) * 8192 + frow * 64 + ((((ln >> 3) & 1) ^ ((frow >> 1) & 3)) << 4);
#define LOAD_WF(m) _Pragma("unroll") for (int f = 0; f < 16; f++) {                                                   \
      const int r = ((f >> 1) * 4 + (m) * 2 + (f & 1)) * 4;                                                           \
      ldmatrix4t(((wfo + unit_of((m) ? FT_U : FT_G, warp >> 1)) ^ ((f & 1) * 32)) + (f >> 1) * 1024, wf[r], wf[r + 1], wf[r + 2], wf[r + 3]); \
    }
    bool early, wait1;
    {
#pragma unroll
      for (int i = 0; i < 16; i += 2) stmatrix4((trow ^ ((i & 7) << 4)) + (i >> 3) * 16384, xr[2 * i], xr[2 * i + 1], xr[2 * i + 2], xr[2 * i + 3]);
      const uint4 cst = lds4(par + PAR_CONST);
      const float A1 = __uint_as_float(cst.x), A2 = __uint_as_float(cst.z);
      uint32_t n = 0;
      early = false; wait1 = false;
#pragma unroll 1
      while (true) {
        uint32_t miss;
        asm volatile("{ .reg .pred p0, p1, p2, p3; .reg .b64 u, v; .reg .b128 w;\n"
                     "setp.ge.u32 p0, %22, 2; setp.ne.and.u32 p0, %4, %21, p0; setp.ne.u32 p1, %8, %21; setp.ne.u32 p2, %12, %21; setp.ne.u32 p3, %16, %21;\n"
                     "@p0 ld.relaxed.gpu.global.v4.u32 {%1, %2, %3, %4}, [%17];\n"
                     "@p1 ld.relaxed.gpu.global.v4.u32 {%5, %6, %7, %8}, [%18];\n"
                     "@p2 ld.relaxed.gpu.global.v4.u32 {%9, %10, %11, %12}, [%19];\n"
                     "@p3 ld.relaxed.gpu.global.v4.u32 {%13, %14, %15, %16}, [%20];\n"
                     "or.pred p0, p0, p1; or.pred p2, p2, p3; or.pred p0, p0, p2; vote.sync.any.pred p0, p0, 0xffffffff; selp.u32 %0, 1, 0, p0; }"
                     : "=r"(miss), "+r"(sv[0].x), "+r"(sv[0].y), "+r"(sv[0].z), "+r"(sv[0].w), "+r"(sv[1].x), "+r"(sv[1].y), "+r"(sv[1].z), "+r"(sv[1].w),
                       "+r"(sv[2].x), "+r"(sv[2].y), "+r"(sv[2].z), "+r"(sv[2].w), "+r"(sv[3].x), "+r"(sv[3].y), "+r"(sv[3].z), "+r"(sv[3].w)
                     : "l"(sp[0]), "l"(sp[1]), "l"(sp[2]), "l"(sp[3]), "r"(tag), "r"(tq) : "memory");
        if (!miss) break;
        wait1 = true;
        if (!early && (b >= NFFN || __all_sync(0xffffffffu, mbar_test(bar_box + (warp >> 1) * 8, 0)))) {
          early = true;
          LOAD_WF(0);
          __syncwarp();
          mbar_arrive_pred(bar_gate, lane0);
        }
        watchdog(n);
      }
      const uint4 v0 = tq < 2 ? own : sv[0], v1 = sv[1], v2 = sv[2], v3 = sv[3];
      PROF(8, ct == PT, 30); STAMP(6);
      float su = (__uint_as_float(v0.x) + __uint_as_float(v1.x)) + (__uint_as_float(v2.x) + __uint_as_float(v3.x));
      float sq = (__uint_as_float(v0.y) + __uint_as_float(v1.y)) + (__uint_as_float(v2.y) + __uint_as_float(v3.y));
      float dt = (__uint_as_float(v0.z) + __uint_as_float(v1.z)) + (__uint_as_float(v2.z) + __uint_as_float(v3.z));
      su += __shfl_xor_sync(0xffffffffu, su, 2); sq += __shfl_xor_sync(0xffffffffu, sq, 2); dt += __shfl_xor_sync(0xffffffffu, dt, 2);
      const float m = su * (1.f / DM);
      float mb, sd;
      ln_scalars(m, fmaxf(sq * (1.f / DM) - m * m, 0.f), mb, sd);
      const float inv = rcp(sd);
      rbest = (dt - mb * A1) * inv + A2;
      mm = pack_bf(mb, mb);
      ih = pack_bf(inv, inv);
      const float lo = inv - bf_lo(ih);
      il = pack_bf(lo, lo);
    }
    int ibest;
    {
      const uint32_t bits = __float_as_uint(rbest);
      const uint32_t key = (((int)bits < 0 ? ~bits : bits | 0x80000000u) & ~0x1ffu) | ((127 - lrow0 - (tq & 1) * 8) << 2) | tag;
      sts1(par + PAR_RED + warp * 4, __reduce_max_sync(0xffffffffu, key));
      PROF(8, ct == PT, 38); STAMP(7);
      uint32_t waited;
      asm volatile("{ .reg .pred p, q; setp.ne.u32 p, %1, 0; barrier.cta.red.or.pred q, 1, 256, p; selp.u32 %0, 1, 0, q; }" : "=r"(waited) : "r"((uint32_t)(wait1 && (wg || CW0))) : "memory");
      const uint4 ka = lds4(par + PAR_RED), kb = lds4(par + PAR_RED + 16);
      const uint32_t k2 = max(max(max(ka.x, ka.y), max(ka.z, ka.w)), max(max(kb.x, kb.y), max(kb.z, kb.w)));
      if (ct == 0 && ((cj & CWM) == 0 || (CWL && !waited))) st_relaxed(g_cand + rb, k2);
      ibest = 127 - ((k2 >> 2) & 127);
    }
    PROF(8, ct == PT, 39); STAMP(8);
    if ((ibest >> 4) == warp) {
      const int src = (ibest & 7) * 4 + ((ibest >> 3) & 1), ch = g * 2;
      const uint32_t cm = __shfl_sync(0xffffffffu, mm, src), ch_ = __shfl_sync(0xffffffffu, ih, src), cl = __shfl_sync(0xffffffffu, il, src);
      const uint32_t xa = res + (ch >> 3) * 16384 + ibest * 128 + (((ch & 7) ^ (ibest & 7)) << 4) + tq * 4;
      const uint32_t x0 = lds1(xa), x1 = lds1(xa ^ 16);
      const uint2 p0 = lds2(par + PAR_T2 + ch * 64 + tq * 16), p1 = lds2(par + PAR_T2 + ch * 64 + 64 + tq * 16);
      uint32_t* dst = g_row + rb * 2 * DM + cj * 128 + ln * 4;
      st_pairs(dst, ln_mod(x0, cm, ch_, cl, p0.x, p0.y), ln_mod(x1, cm, ch_, cl, p1.x, p1.y), tag);
      st_pairs(dst + DM, x0, x1, tag);
      __syncwarp();
    }
    PROF(8, ct == PT, 37); STAMP(9);
    uint32_t wd[64];
    const uint32_t wda = base + unit_of(FT_D, warp >> 1) + (warp & 1) * 8192 + frow * 128 + ((((ln >> 3) & 1) ^ (ln & 7)) << 4);
#define LOAD_WD(f) ldmatrix4t((wda ^ ((((f) >> 1) & 3) * 32)) + ((f) >> 3) * 4096 + ((f) & 1) * 2048, wd[4 * (f)], wd[4 * (f) + 1], wd[4 * (f) + 2], wd[4 * (f) + 3])
    if (!early) {
      if (b < NFFN) mbar_wait(bar_box + (warp >> 1) * 8, 0);
      LOAD_WF(0);
      __syncwarp();
      mbar_arrive_pred(bar_gate, lane0);
    }
    if (b < NFFN) {
      const uint32_t own = base + unit_of(FT_G, warp >> 1) + (warp & 1) * 8192;
      mbar_wait(bar_box + (4 + (warp >> 1)) * 8, 0);
      LOAD_WF(1);
      uint32_t* const ydst = g_ypart + ((size_t)(warp * 16 + tq * 2) * NFFN + b) * 8 + g;
      PROF(8, ct == PT, 31); STAMP(10);
      mbar_wait(bar_box + (8 + (warp >> 1)) * 8, 0);
#pragma unroll
      for (int f = 0; f < WDE; f++) LOAD_WD(f);
      STAMP(11);
      mbar_wait(bar_sel, 0);
      PROF(8, ct == PT, 33); STAMP(12);
      float d[8][4];
#pragma unroll
      for (int i = 0; i < 4; i++) { d[i][0] = 0.f; d[i][1] = 0.f; d[i][2] = 0.f; d[i][3] = 0.f; }
#pragma unroll
      for (int ks = 0; ks < 8; ks++) {
        const uint2 hb = lds2(own + 256 + ks * 32 + tq * 8);
#pragma unroll
        for (int mt = 0; mt < 4; mt++) {
          const int r = ks * 16 + mt * 4;
          mma16816(d[mt], wf[r], wf[r + 1], wf[r + 2], wf[r + 3], hb.x, hb.y);
        }
      }
      sts2(own + (tq * 8 + g) * 8, __float_as_uint((tq & 2) ? ((tq & 1) ? d[1][2] : d[1][0]) : ((tq & 1) ? d[0][2] : d[0][0])),
           __float_as_uint((tq & 2) ? ((tq & 1) ? d[3][2] : d[3][0]) : ((tq & 1) ? d[2][2] : d[2][0])));
      bar_sync(1, 256);
      uint32_t ab[4];
      {
        float G = 0.f, U = 0.f;
        uint2 pv[8];
#pragma unroll
        for (int w8 = 0; w8 < 8; w8++) pv[w8] = lds2(base + ln * 8 + ((FT_G >> (w8 >> 1) * 4) & 15) * UNIT + (w8 & 1) * 8192);
#pragma unroll
        for (int w8 = 0; w8 < 8; w8 += 2) {
          G += __uint_as_float(pv[w8].x) + __uint_as_float(pv[w8 + 1].x);
          U += __uint_as_float(pv[w8].y) + __uint_as_float(pv[w8 + 1].y);
        }
#pragma unroll
        for (int f = WDE; f < 16; f++) LOAD_WD(f);
        const float act = rbf(silu_f(rbf(G))) * rbf(U);
        const uint32_t pk = pack_bf(act, __shfl_down_sync(0xffffffffu, act, 1));
#pragma unroll
        for (int i = 0; i < 4; i++) ab[i] = __shfl_sync(0xffffffffu, pk, i * 8 + tq * 2);
      }
      PROF(8, ct == PT, 34); STAMP(13);
#pragma unroll
      for (int mt = 0; mt < 8; mt++) {
        d[mt][0] = 0.f; d[mt][1] = 0.f; d[mt][2] = 0.f; d[mt][3] = 0.f;
        mma16816(d[mt], wd[mt * 8], wd[mt * 8 + 1], wd[mt * 8 + 2], wd[mt * 8 + 3], ab[0], ab[1]);
        mma16816(d[mt], wd[mt * 8 + 4], wd[mt * 8 + 5], wd[mt * 8 + 6], wd[mt * 8 + 7], ab[2], ab[3]);
      }
#pragma unroll
      for (int i = 0; i < 4; i++) {
        const int m4 = (i >> 1) * 4, e = (i & 1) * 2;
        const float y = (tq & 2) ? ((tq & 1) ? d[m4 + 3][e] : d[m4 + 2][e]) : ((tq & 1) ? d[m4 + 1][e] : d[m4][e]);
        st_relaxed(ydst + (m4 * 2 + (i & 1)) * NFFN * 8, tagf(y, tag));
      }
      PROF(8, ct == PT, 35); STAMP(14);
    }
    mbar_wait(bar_sel, 0);
    mbar_arrive_pred(bar_win, ct == 0);
    const int iwin = lds1(par + PAR_CONST + 60) & 0x7ff;
    {
      const uint32_t mm0 = __shfl_sync(0xffffffffu, mm, ln & ~1), mm1 = __shfl_sync(0xffffffffu, mm, ln | 1);
      const uint32_t ih0 = __shfl_sync(0xffffffffu, ih, ln & ~1), ih1 = __shfl_sync(0xffffffffu, ih, ln | 1);
      const uint32_t il0 = __shfl_sync(0xffffffffu, il, ln & ~1), il1 = __shfl_sync(0xffffffffu, il, ln | 1);
      const bool mine = (iwin >> 4) == rb * 8 + warp;
#pragma unroll 1
      for (int hf = 0; hf < 2; hf++) {
        uint32_t x[16];
#pragma unroll
        for (int i = 0; i < 8; i += 2) ldmatrix4((trow ^ (i << 4)) + hf * 16384, x[2 * i], x[2 * i + 1], x[2 * i + 2], x[2 * i + 3]);
#pragma unroll
        for (int i = 0; i < 8; i++) {
          const uint4 pv = lds4(par + PAR_T2 + (hf * 8 + i) * 64 + tq * 16);
          x[2 * i] = hadd2(x[2 * i], hmul2(pv.z, ln_mod(x[2 * i], mm0, ih0, il0, pv.x, pv.y)));
          x[2 * i + 1] = hadd2(x[2 * i + 1], hmul2(pv.z, ln_mod(x[2 * i + 1], mm1, ih1, il1, pv.x, pv.y)));
        }
        if (mine) {
          uint32_t* dst = reinterpret_cast<uint32_t*>(P.out + (size_t)grow0 * DM + cj * 128 + hf * 64) + tq;
#pragma unroll
          for (int i = 0; i < 8; i++) {
            if (grow0 != iwin) dst[i * 4] = x[2 * i];
            if (grow0 + 8 != iwin) dst[i * 4 + 4 * DM] = x[2 * i + 1];
          }
        } else {
#pragma unroll
          for (int i = 0; i < 8; i += 2) stmatrix4((trow ^ (i << 4)) + hf * 16384, x[2 * i], x[2 * i + 1], x[2 * i + 2], x[2 * i + 3]);
          fence_async_smem();
          __syncwarp();
          if (elect_one()) {
            tma2d_store(&maps.out, res + hf * 16384 + warp * 2048, cj * 128 + hf * 64, rb * 128 + warp * 16);
            asm volatile("cp.async.bulk.commit_group;" ::: "memory");
          }
        }
      }
      asm volatile("cp.async.bulk.wait_group.read 0;" ::: "memory");
    }
    PROF(8, ct == PT, 11); STAMP(15);
    cluster_wait();
  }
}

typedef CUresult (*EncodeFn)(CUtensorMap*, CUtensorMapDataType, cuuint32_t, void*, const cuuint64_t*, const cuuint64_t*,
                             const cuuint32_t*, const cuuint32_t*, CUtensorMapInterleave, CUtensorMapSwizzle,
                             CUtensorMapL2promotion, CUtensorMapFloatOOBfill);

void map2d(EncodeFn enc, CUtensorMap* m, const void* p, uint64_t rows, uint64_t cols, uint32_t brows) {
  cuuint64_t dims[2] = {cols, rows}, strides[1] = {cols * 2};
  cuuint32_t box[2] = {64, brows}, es[2] = {1, 1};
  enc(m, CU_TENSOR_MAP_DATA_TYPE_BFLOAT16, 2, const_cast<void*>(p), dims, strides, box, es, CU_TENSOR_MAP_INTERLEAVE_NONE,
      CU_TENSOR_MAP_SWIZZLE_128B, CU_TENSOR_MAP_L2_PROMOTION_L2_256B, CU_TENSOR_MAP_FLOAT_OOB_FILL_NONE);
}
void map2d_narrow(EncodeFn enc, CUtensorMap* m, const void* p, uint64_t rows, uint64_t cols, uint32_t brows) {
  cuuint64_t dims[2] = {cols, rows}, strides[1] = {cols * 2};
  cuuint32_t box[2] = {32, brows}, es[2] = {1, 1};
  enc(m, CU_TENSOR_MAP_DATA_TYPE_BFLOAT16, 2, const_cast<void*>(p), dims, strides, box, es, CU_TENSOR_MAP_INTERLEAVE_NONE,
      CU_TENSOR_MAP_SWIZZLE_64B, CU_TENSOR_MAP_L2_PROMOTION_L2_64B, CU_TENSOR_MAP_FLOAT_OOB_FILL_NONE);
}
void map3d(EncodeFn enc, CUtensorMap* m, const void* p, uint64_t rows, uint64_t cols, uint32_t brows, uint32_t nch) {
  cuuint64_t dims[3] = {64, rows, cols / 64}, strides[2] = {cols * 2, 128};
  cuuint32_t box[3] = {64, brows, nch}, es[3] = {1, 1, 1};
  enc(m, CU_TENSOR_MAP_DATA_TYPE_BFLOAT16, 3, const_cast<void*>(p), dims, strides, box, es, CU_TENSOR_MAP_INTERLEAVE_NONE,
      CU_TENSOR_MAP_SWIZZLE_128B, CU_TENSOR_MAP_L2_PROMOTION_L2_256B, CU_TENSOR_MAP_FLOAT_OOB_FILL_NONE);
}

}

extern "C" void kernel_launch(void* const* d_in, const int* in_sizes, int n_in, void* d_out, int out_size) {
  (void)in_sizes; (void)n_in; (void)out_size;
  static EncodeFn enc = nullptr;
  if (!enc) {
    void* fn = nullptr;
    cudaDriverEntryPointQueryResult st;
    cudaGetDriverEntryPoint("cuTensorMapEncodeTiled", &fn, cudaEnableDefault, &st);
    enc = (EncodeFn)fn;
    cudaFuncSetAttribute(fused_kernel, cudaFuncAttributeMaxDynamicSharedMemorySize, SMEM_BYTES);
  }
  Maps maps;
  map2d(enc, &maps.x, d_in[0], SEQ, DM, 128);
  map2d(enc, &maps.out, d_out, SEQ, DM, 16);
  map3d(enc, &maps.wq, d_in[3], DM, NQ, 64, 2);
  map3d(enc, &maps.k, d_in[1], 4 * SK, 128, 128, 1);
  map3d(enc, &maps.v, d_in[2], 4 * SK, 128, 128, 1);
  map3d(enc, &maps.wo, d_in[4], NQ, DM, 64, 2);
  map2d_narrow(enc, &maps.wg, d_in[7], DM, FF, 256);
  map2d_narrow(enc, &maps.wu, d_in[8], DM, FF, 256);
  map3d(enc, &maps.wd, d_in[9], FF, DM, 32, 4);
  map2d_narrow(enc, &maps.wm, d_in[11], DM, NMOD, 256);
  Ptrs p;
  p.x = (const __nv_bfloat16*)d_in[0];
  p.w_r = (const __nv_bfloat16*)d_in[6];
  p.w_gate = (const __nv_bfloat16*)d_in[7];
  p.w_up = (const __nv_bfloat16*)d_in[8];
  p.w_down = (const __nv_bfloat16*)d_in[9];
  p.c = (const __nv_bfloat16*)d_in[10];
  p.w_mod = (const __nv_bfloat16*)d_in[11];
  p.out = (__nv_bfloat16*)d_out;
  fused_kernel<<<NMAIN + NHELP, 384, SMEM_BYTES>>>(maps, p);
}
```

```cpp
#include <cuda_runtime.h>
#include <cuda_bf16.h>
#include <cuda.h>
#include <stdint.h>
#include <type_traits>

#define HD 1
#define HDX 2
#define XF 4
#define XE 32
#define XR 0
#define PF2 1
#define PF2T 4
#define NRS 6
#define FPACE 3
#define GOST 20
#define WB 2
#define WN 24
#define RES0 17
#define RES1 20
#define HU 32
#define NS1 6
#define PD0 40
#define PG0 31
#define PSL 0
#define CWM 7
#define WDE 16
#define CWL 1
#define CW0 0
#define ESV 1
#define PPOS 1
#define FB0 0
#define FB2 8
#define OPS 8192
#define OFL 0
#define ODS 8
#define VREL 7
#define E0 3

namespace {

constexpr int SEQ = 2048, DM = 1024, NQ = 4096, SK = 2048, WIN = 512, FF = 3584, NMOD = 6144;
constexpr int NMAIN = 128, NHELP = 4, NFFN = 112;
constexpr int NSLOT = 4, SLOT_BYTES = 32768, UNIT = 16384, GST_BYTES = 3 * UNIT;
constexpr uint32_t XT1 = 0xDCBA, XT2 = 0x9687;
constexpr uint32_t WT0 = 0xA741, WT1 = 0x7420, WT2 = 0x4A20;
constexpr uint32_t AT0 = WT1, AT1 = WT2;
constexpr uint32_t QT = 0xDC9696DC;
constexpr int OFF_STAGE = 12 * UNIT;
constexpr uint32_t FT_G = 0x07B3, FT_U = 0xA628, FT_D = 0x5149;
constexpr int OFF_RES = 12 * UNIT;
constexpr int OFF_PAR = 14 * UNIT;
constexpr int OFF_BAR = OFF_PAR + 2528;
constexpr int SMEM_BYTES = OFF_BAR + 544;
static_assert(SMEM_BYTES <= 232448, "smem");

constexpr int PAR_T1 = 0;
constexpr int PAR_T2 = 512;
constexpr int PAR_CONST = 1536;
constexpr int PAR_RED = 1600;
constexpr int PAR_SINK = 2176;

struct Maps {
  CUtensorMap x, wq, k, v, wo, wg, wu, wd, wm, out;
};
struct Ptrs {
  const __nv_bfloat16 *x, *w_r, *c, *w_mod, *w_gate, *w_up, *w_down;
  __nv_bfloat16* out;
};

__device__ __align__(1024) uint8_t g_act[16 * 80 * UNIT];
__device__ __align__(128) uint32_t g_mod[NMOD];
__device__ __align__(128) uint32_t g_modp[2 * 2 * DM];
__device__ __align__(128) uint32_t g_ln1[SEQ * 4];
__device__ __align__(128) uint32_t g_cnt_h[16 * 32];
__device__ __align__(128) uint32_t g_cnt_o[128 * 32];
__device__ __align__(128) uint32_t g_xch[NMAIN * 8 * 256 * 4];
__device__ __align__(128) uint32_t g_stats[8 * SEQ * 4];
__device__ __align__(128) uint32_t g_cand[32];
__device__ __align__(128) uint32_t g_row[16 * 2 * DM];
__device__ __align__(128) uint32_t g_ypart[NMAIN * NFFN * 8];
__device__ uint32_t g_epoch;

__device__ __forceinline__ uint32_t fresh_lane() { uint32_t l; asm volatile("mov.u32 %0, %%laneid;" : "=r"(l)); return l; }
__device__ __forceinline__ uint32_t frag_offset(int warp) {
  const uint32_t l = fresh_lane();
  return ((warp & 3) * 16 + (l & 15)) * 128 + (((l >> 4) ^ (l & 7)) << 4);
}
__device__ __forceinline__ bool elect_one() {
  uint32_t p;
  asm volatile("{ .reg .pred q; elect.sync _|q, 0xffffffff; selp.u32 %0, 1, 0, q; }" : "=r"(p));
  return p;
}
__device__ __forceinline__ uint32_t smem_u32(const void* p) { return (uint32_t)__cvta_generic_to_shared(p); }
__device__ __forceinline__ void mbar_init(uint32_t bar, uint32_t cnt) {
  asm volatile("mbarrier.init.shared::cta.b64 [%0], %1;" ::"r"(bar), "r"(cnt) : "memory");
}
__device__ __forceinline__ void mbar_expect_tx(uint32_t bar, uint32_t bytes) {
  asm volatile("mbarrier.arrive.expect_tx.shared::cta.b64 _, [%0], %1;" ::"r"(bar), "r"(bytes) : "memory");
}
__device__ __forceinline__ void mbar_arrive(uint32_t bar) {
  asm volatile("mbarrier.arrive.shared::cta.b64 _, [%0];" ::"r"(bar) : "memory");
}
__device__ __forceinline__ void mbar_arrive_pred(uint32_t bar, bool p) {
  asm volatile("{ .reg .pred p; setp.ne.b32 p, %1, 0; @p mbarrier.arrive.shared::cta.b64 _, [%0]; }" ::"r"(bar), "r"((int)p) : "memory");
}
__device__ __forceinline__ void mbar_arrive_cl(uint32_t bar, uint32_t off, bool p = true) {
  asm volatile("{ .reg .pred p, q; .reg .b32 a; setp.ne.b32 q, %2, 0; setp.ne.and.b32 p, %0, 0, q; add.u32 a, %0, %1; @p mbarrier.arrive.shared::cluster.b64 _, [a]; }"
               ::"r"(bar), "r"(off), "r"((int)p) : "memory");
}
__device__ __forceinline__ uint32_t mapa(uint32_t addr, uint32_t cta) {
  uint32_t r; asm("mapa.shared::cluster.u32 %0, %1, %2;" : "=r"(r) : "r"(addr), "r"(cta)); return r;
}
__device__ __forceinline__ void cluster_arrive() { asm volatile("barrier.cluster.arrive.relaxed.aligned;" ::: "memory"); }
__device__ __forceinline__ void cluster_wait() { asm volatile("barrier.cluster.wait.aligned;" ::: "memory"); }
__device__ __forceinline__ void watchdog(uint32_t& n) {
}
__device__ __forceinline__ void mbar_wait(uint32_t bar, uint32_t parity) {
  asm volatile("{\n.reg .pred p;\nWAIT_%=:\nmbarrier.try_wait.parity.shared::cta.b64 p, [%0], %1;\n@!p bra WAIT_%=;\n}" ::"r"(bar), "r"(parity) : "memory");
}
__device__ __forceinline__ bool mbar_test(uint32_t bar, uint32_t parity) {
  uint32_t ok;
  asm volatile("{\n.reg .pred p;\nmbarrier.test_wait.parity.shared::cta.b64 p, [%1], %2;\nselp.u32 %0, 1, 0, p;\n}" : "=r"(ok) : "r"(bar), "r"(parity) : "memory");
  return ok;
}
__device__ __forceinline__ uint64_t l2_stream() {
  uint64_t f; asm("createpolicy.fractional.L2::evict_first.b64 %0, 1.0;" : "=l"(f)); return f;
}
__device__ __forceinline__ void tma2d(uint32_t dst, const CUtensorMap* m, int c0, int c1, uint32_t bar) {
  asm volatile("cp.async.bulk.tensor.2d.shared::cluster.global.mbarrier::complete_tx::bytes.L2::cache_hint [%0], [%1, {%3, %4}], [%2], %5;"
               ::"r"(dst), "l"(m), "r"(bar), "r"(c0), "r"(c1), "l"(l2_stream()) : "memory");
}
__device__ __forceinline__ void tma3d_prefetch(const CUtensorMap* m, int c0, int c1, int c2) {
  asm volatile("cp.async.bulk.prefetch.tensor.3d.L2.global.tile [%0, {%1, %2, %3}];" ::"l"(m), "r"(c0), "r"(c1), "r"(c2) : "memory");
}
__device__ __forceinline__ void bulk_load(uint32_t dst, const void* src, uint32_t bytes, uint32_t bar) {
  asm volatile("cp.async.bulk.shared::cluster.global.mbarrier::complete_tx::bytes [%0], [%1], %2, [%3];" ::"r"(dst), "l"(src), "r"(bytes), "r"(bar) : "memory");
}
__device__ __forceinline__ void bulk_load_stream(uint32_t dst, const void* src, uint32_t bytes, uint32_t bar) {
  asm volatile("cp.async.bulk.shared::cluster.global.mbarrier::complete_tx::bytes.L2::cache_hint [%0], [%1], %2, [%3], %4;"
               ::"r"(dst), "l"(src), "r"(bytes), "r"(bar), "l"(l2_stream()) : "memory");
}
__device__ __forceinline__ void tma2d_store(const CUtensorMap* m, uint32_t src, int c0, int c1) {
  asm volatile("cp.async.bulk.tensor.2d.global.shared::cta.bulk_group [%0, {%2, %3}], [%1];" ::"l"(m), "r"(src), "r"(c0), "r"(c1) : "memory");
}
__device__ __forceinline__ void bulk_store(void* dst, uint32_t src, uint32_t bytes) {
  asm volatile("cp.async.bulk.global.shared::cta.bulk_group [%0], [%1], %2;" ::"l"(dst), "r"(src), "r"(bytes) : "memory");
}
__device__ __forceinline__ uint32_t unit_of(uint32_t table, uint32_t i) { return ((table >> (i * 4)) & 15) * UNIT; }
__device__ __forceinline__ void tma3d(uint32_t dst, const CUtensorMap* m, int c0, int c1, int c2, uint32_t bar) {
  asm volatile("cp.async.bulk.tensor.3d.shared::cluster.global.mbarrier::complete_tx::bytes.L2::cache_hint [%0], [%1, {%3, %4, %5}], [%2], %6;"
               ::"r"(dst), "l"(m), "r"(bar), "r"(c0), "r"(c1), "r"(c2), "l"(l2_stream()) : "memory");
}
template <bool STREAM>
__device__ __forceinline__ void tma3d_mc(uint32_t dst, const CUtensorMap* m, int c0, int c1, int c2, uint32_t bar) {
  if (STREAM)
    asm volatile("cp.async.bulk.tensor.3d.shared::cluster.global.mbarrier::complete_tx::bytes.multicast::cluster.L2::cache_hint [%0], [%1, {%3, %4, %5}], [%2], %6, %7;"
                 ::"r"(dst), "l"(m), "r"(bar), "r"(c0), "r"(c1), "r"(c2), "h"((uint16_t)3), "l"(l2_stream()) : "memory");
  else
    asm volatile("cp.async.bulk.tensor.3d.shared::cluster.global.mbarrier::complete_tx::bytes.multicast::cluster [%0], [%1, {%3, %4, %5}], [%2], %6;"
                 ::"r"(dst), "l"(m), "r"(bar), "r"(c0), "r"(c1), "r"(c2), "h"((uint16_t)3) : "memory");
}
__device__ __forceinline__ void prefetch_map(const CUtensorMap* m) {
  asm volatile("prefetch.tensormap [%0];" ::"l"(m) : "memory");
}
__device__ __forceinline__ void fence_async() { asm volatile("fence.proxy.async.global;" ::: "memory"); }
__device__ __forceinline__ void fence_async_smem() { asm volatile("fence.proxy.async.shared::cta;" ::: "memory"); }
__device__ __forceinline__ void bar_sync(int id, int n) { asm volatile("bar.sync %0, %1;" ::"r"(id), "r"(n) : "memory"); }
__device__ __forceinline__ void bar_arrive(int id, int n) { asm volatile("bar.arrive %0, %1;" ::"r"(id), "r"(n) : "memory"); }
__device__ __forceinline__ void wg_fence() { asm volatile("wgmma.fence.sync.aligned;" ::: "memory"); }
__device__ __forceinline__ void wg_commit() { asm volatile("wgmma.commit_group.sync.aligned;" ::: "memory"); }
template <int N> __device__ __forceinline__ void wg_wait() { asm volatile("wgmma.wait_group.sync.aligned %0;" ::"n"(N) : "memory"); }
__device__ __forceinline__ uint64_t make_desc(uint32_t addr, uint32_t lbo, uint32_t sbo) {
  return (uint64_t)((addr & 0x3FFFF) >> 4) | ((uint64_t)(lbo >> 4) << 16) | ((uint64_t)(sbo >> 4) << 32) | (1ull << 62);
}
__device__ __forceinline__ uint32_t ld_relaxed(const uint32_t* p) {
  uint32_t v; asm volatile("ld.relaxed.gpu.global.u32 %0, [%1];" : "=r"(v) : "l"(p) : "memory"); return v;
}
__device__ __forceinline__ uint32_t ld_acquire(const uint32_t* p) {
  uint32_t v; asm volatile("ld.acquire.gpu.global.u32 %0, [%1];" : "=r"(v) : "l"(p) : "memory"); return v;
}
__device__ __forceinline__ uint4 ld_relaxed4(const uint32_t* p) {
  uint4 v; asm volatile("ld.relaxed.gpu.global.v4.u32 {%0,%1,%2,%3}, [%4];" : "=r"(v.x), "=r"(v.y), "=r"(v.z), "=r"(v.w) : "l"(p) : "memory"); return v;
}
__device__ __forceinline__ uint2 ld_relaxed2(const uint32_t* p) {
  uint2 v; asm volatile("ld.relaxed.gpu.global.v2.u32 {%0,%1}, [%2];" : "=r"(v.x), "=r"(v.y) : "l"(p) : "memory"); return v;
}
__device__ __forceinline__ void st_relaxed(uint32_t* p, uint32_t v) {
  asm volatile("st.relaxed.gpu.global.u32 [%0], %1;" ::"l"(p), "r"(v) : "memory");
}
__device__ __forceinline__ void st_relaxed2(uint32_t* p, uint32_t a, uint32_t b) {
  asm volatile("st.relaxed.gpu.global.v2.u32 [%0], {%1,%2};" ::"l"(p), "r"(a), "r"(b) : "memory");
}
__device__ __forceinline__ void st_relaxed4(uint32_t* p, uint32_t a, uint32_t b, uint32_t c, uint32_t d) {
  asm volatile("st.relaxed.gpu.global.v4.u32 [%0], {%1,%2,%3,%4};" ::"l"(p), "r"(a), "r"(b), "r"(c), "r"(d) : "memory");
}
__device__ __forceinline__ void st_b128(uint32_t* p, uint32_t a, uint32_t b, uint32_t c, uint32_t d) {
  asm volatile("{ .reg .b64 u, v; .reg .b128 w; mov.b64 u, {%1, %2}; mov.b64 v, {%3, %4}; mov.b128 w, {u, v}; st.relaxed.gpu.global.b128 [%0], w; }"
               ::"l"(p), "r"(a), "r"(b), "r"(c), "r"(d) : "memory");
}
__device__ __forceinline__ uint4 ld_b128(const uint32_t* p) {
  uint4 r;
  asm volatile("{ .reg .b64 u, v; .reg .b128 w; ld.relaxed.gpu.global.b128 w, [%4]; mov.b128 {u, v}, w; mov.b64 {%0, %1}, u; mov.b64 {%2, %3}, v; }"
               : "=r"(r.x), "=r"(r.y), "=r"(r.z), "=r"(r.w) : "l"(p) : "memory");
  return r;
}
__device__ __forceinline__ void st_pairs(uint32_t* p, uint32_t a, uint32_t b, uint32_t tag) {
  asm volatile("{ .reg .b64 u, v; mov.b64 u, {%1, %3}; mov.b64 v, {%2, %3}; st.relaxed.gpu.global.v2.b64 [%0], {u, v}; }"
               ::"l"(p), "r"(a), "r"(b), "r"(tag) : "memory");
}
__device__ __forceinline__ uint4 ld_pairs(const uint32_t* p) {
  uint4 v;
  asm volatile("{ .reg .b64 u, v; ld.relaxed.gpu.global.v2.b64 {u, v}, [%4]; mov.b64 {%0, %1}, u; mov.b64 {%2, %3}, v; }"
               : "=r"(v.x), "=r"(v.y), "=r"(v.z), "=r"(v.w) : "l"(p) : "memory");
  return v;
}
__device__ __forceinline__ uint2 ld_pair(const uint32_t* p) {
  uint2 v;
  asm volatile("{ .reg .b64 u; ld.relaxed.gpu.global.b64 u, [%2]; mov.b64 {%0, %1}, u; }" : "=r"(v.x), "=r"(v.y) : "l"(p) : "memory");
  return v;
}
__device__ __forceinline__ void red_release(uint32_t* p, uint32_t v) {
  asm volatile("red.release.gpu.global.add.u32 [%0], %1;" ::"l"(p), "r"(v) : "memory");
}
__device__ __forceinline__ uint32_t ldg_nc1(const void* p) {
  uint32_t v;
  asm volatile("ld.global.nc.u32 %0, [%1];" : "=r"(v) : "l"(p));
  return v;
}
__device__ __forceinline__ uint4 ldg_nc4(const void* p) {
  uint4 v; asm volatile("ld.global.nc.L1::no_allocate.v4.u32 {%0,%1,%2,%3}, [%4];" : "=r"(v.x), "=r"(v.y), "=r"(v.z), "=r"(v.w) : "l"(p)); return v;
}
__device__ __forceinline__ uint4 ldg_stream4(const void* p) {
  uint4 v;
  asm volatile("ld.global.nc.L1::no_allocate.L2::cache_hint.v4.u32 {%0,%1,%2,%3}, [%4], %5;" : "=r"(v.x), "=r"(v.y), "=r"(v.z), "=r"(v.w) : "l"(p), "l"(l2_stream()));
  return v;
}
__device__ __forceinline__ void stg4(void* p, uint4 v) {
  asm volatile("st.global.v4.u32 [%0], {%1,%2,%3,%4};" ::"l"(p), "r"(v.x), "r"(v.y), "r"(v.z), "r"(v.w) : "memory");
}
__device__ __forceinline__ void wait_counter(const uint32_t* p, uint32_t target) {
  uint32_t n = 0;
  while ((int)(ld_acquire(p) - target) < 0) { watchdog(n); }
}
__device__ __forceinline__ uint32_t tagf(float v, uint32_t tag) { return (__float_as_uint(v) & ~3u) | tag; }
__device__ __forceinline__ bool tag_ok(uint4 v, uint32_t tag) { return (((v.x ^ tag) | (v.y ^ tag) | (v.z ^ tag) | (v.w ^ tag)) & 3u) == 0; }
__device__ __forceinline__ float untag_sum(uint32_t a, uint32_t b) { return __uint_as_float(a & ~3u) + __uint_as_float(b & ~3u); }
__device__ __forceinline__ uint4 poll4(const uint32_t* p, uint32_t tag) {
  uint4 v = ld_relaxed4(p);
  uint32_t n = 0;
  while (!tag_ok(v, tag)) { v = ld_relaxed4(p); watchdog(n); }
  return v;
}
__device__ __forceinline__ float bf_lo(uint32_t v) { return __uint_as_float(v << 16); }
__device__ __forceinline__ float bf_hi(uint32_t v) { return __uint_as_float(v & 0xffff0000u); }
__device__ __forceinline__ uint32_t pack_bf(float lo, float hi) {
  uint32_t r; asm("cvt.rn.bf16x2.f32 %0, %1, %2;" : "=r"(r) : "f"(hi), "f"(lo)); return r;
}
__device__ __forceinline__ float rbf(float v) { return __uint_as_float(pack_bf(0.f, v) & 0xffff0000u); }
__device__ __forceinline__ uint32_t hmul2(uint32_t a, uint32_t b) {
  uint32_t r; asm("mul.rn.bf16x2 %0, %1, %2;" : "=r"(r) : "r"(a), "r"(b)); return r;
}
__device__ __forceinline__ uint32_t hadd2(uint32_t a, uint32_t b) {
  uint32_t r; asm("add.rn.bf16x2 %0, %1, %2;" : "=r"(r) : "r"(a), "r"(b)); return r;
}
__device__ __forceinline__ uint32_t hsub2(uint32_t a, uint32_t b) {
  uint32_t r; asm("sub.rn.bf16x2 %0, %1, %2;" : "=r"(r) : "r"(a), "r"(b)); return r;
}
__device__ __forceinline__ uint32_t hmax2(uint32_t a, uint32_t b) {
  uint32_t r; asm("max.bf16x2 %0, %1, %2;" : "=r"(r) : "r"(a), "r"(b)); return r;
}
__device__ __forceinline__ float rcp(float x) { float r; asm("rcp.approx.ftz.f32 %0, %1;" : "=f"(r) : "f"(x)); return r; }
__device__ __forceinline__ float ex2(float x) { float r; asm("ex2.approx.ftz.f32 %0, %1;" : "=f"(r) : "f"(x)); return r; }
__device__ __forceinline__ void stmatrix4(uint32_t addr, uint32_t a, uint32_t b, uint32_t c, uint32_t d) {
  asm volatile("stmatrix.sync.aligned.m8n8.x4.shared.b16 [%0], {%1,%2,%3,%4};" ::"r"(addr), "r"(a), "r"(b), "r"(c), "r"(d) : "memory");
}
__device__ __forceinline__ void ldmatrix4(uint32_t addr, uint32_t& a, uint32_t& b, uint32_t& c, uint32_t& d) {
  asm volatile("ldmatrix.sync.aligned.m8n8.x4.shared.b16 {%0,%1,%2,%3}, [%4];" : "=r"(a), "=r"(b), "=r"(c), "=r"(d) : "r"(addr) : "memory");
}
__device__ __forceinline__ void ldmatrix4t(uint32_t addr, uint32_t& a, uint32_t& b, uint32_t& c, uint32_t& d) {
  asm volatile("ldmatrix.sync.aligned.m8n8.x4.trans.shared.b16 {%0,%1,%2,%3}, [%4];" : "=r"(a), "=r"(b), "=r"(c), "=r"(d) : "r"(addr) : "memory");
}
__device__ __forceinline__ void mma16816(float (&d)[4], uint32_t a0, uint32_t a1, uint32_t a2, uint32_t a3, uint32_t b0, uint32_t b1) {
  asm volatile("mma.sync.aligned.m16n8k16.row.col.f32.bf16.bf16.f32 {%0,%1,%2,%3}, {%4,%5,%6,%7}, {%8,%9}, {%0,%1,%2,%3};"
               : "+f"(d[0]), "+f"(d[1]), "+f"(d[2]), "+f"(d[3]) : "r"(a0), "r"(a1), "r"(a2), "r"(a3), "r"(b0), "r"(b1));
}
__device__ __forceinline__ void sts1(uint32_t a, uint32_t v) { asm volatile("st.shared.u32 [%0], %1;" ::"r"(a), "r"(v) : "memory"); }
__device__ __forceinline__ uint4 lds4(uint32_t a) {
  uint4 v; asm volatile("ld.shared.v4.u32 {%0,%1,%2,%3}, [%4];" : "=r"(v.x), "=r"(v.y), "=r"(v.z), "=r"(v.w) : "r"(a) : "memory"); return v;
}
__device__ __forceinline__ uint2 lds2(uint32_t a) {
  uint2 v; asm volatile("ld.shared.v2.u32 {%0,%1}, [%2];" : "=r"(v.x), "=r"(v.y) : "r"(a) : "memory"); return v;
}
__device__ __forceinline__ uint32_t lds1(uint32_t a) {
  uint32_t v; asm volatile("ld.shared.u32 %0, [%1];" : "=r"(v) : "r"(a) : "memory"); return v;
}
__device__ __forceinline__ void sts2(uint32_t a, uint32_t x, uint32_t y) { asm volatile("st.shared.v2.u32 [%0], {%1,%2};" ::"r"(a), "r"(x), "r"(y) : "memory"); }
__device__ __forceinline__ void sts4(uint32_t a, uint4 v) {
  asm volatile("st.shared.v4.u32 [%0], {%1,%2,%3,%4};" ::"r"(a), "r"(v.x), "r"(v.y), "r"(v.z), "r"(v.w) : "memory");
}
__device__ __forceinline__ float silu_f(float v) { return __fdividef(v, 1.f + __expf(-v)); }
__device__ __forceinline__ uint32_t hfma2(uint32_t a, uint32_t b, uint32_t c) {
  uint32_t r; asm("fma.rn.bf16x2 %0, %1, %2, %3;" : "=r"(r) : "r"(a), "r"(b), "r"(c)); return r;
}
__device__ __forceinline__ void split_inv(float sd, uint32_t& ih, uint32_t& il) {
  const float inv = rcp(sd);
  ih = pack_bf(inv, inv);
  const float lo = inv - bf_lo(ih);
  il = pack_bf(lo, lo);
}
__device__ __forceinline__ uint32_t ln_mod(uint32_t x, uint32_t mean2, uint32_t ih, uint32_t il, uint32_t c1, uint32_t sh) {
  const uint32_t d = hsub2(x, mean2);
  return hadd2(hmul2(hfma2(d, ih, hmul2(d, il)), c1), sh);
}

#define R8(a, i) "+f"(a[i]), "+f"(a[i + 1]), "+f"(a[i + 2]), "+f"(a[i + 3]), "+f"(a[i + 4]), "+f"(a[i + 5]), "+f"(a[i + 6]), "+f"(a[i + 7])
#define D64 "{%0,%1,%2,%3,%4,%5,%6,%7,%8,%9,%10,%11,%12,%13,%14,%15,%16,%17,%18,%19,%20,%21,%22,%23,%24,%25,%26,%27,%28,%29,%30,%31," \
            "%32,%33,%34,%35,%36,%37,%38,%39,%40,%41,%42,%43,%44,%45,%46,%47,%48,%49,%50,%51,%52,%53,%54,%55,%56,%57,%58,%59,%60,%61,%62,%63}"
template <int TB>
__device__ __forceinline__ void mma_ss(float (&d)[64], uint64_t da, uint64_t db, int sc) {
  asm volatile("{\n.reg .pred p;\nsetp.ne.b32 p, %66, 0;\n"
               "wgmma.mma_async.sync.aligned.m64n128k16.f32.bf16.bf16 " D64 ", %64, %65, p, 1, 1, 0, %67;\n}"
               : R8(d, 0), R8(d, 8), R8(d, 16), R8(d, 24), R8(d, 32), R8(d, 40), R8(d, 48), R8(d, 56)
               : "l"(da), "l"(db), "r"(sc), "n"(TB));
}
template <int TB>
__device__ __forceinline__ void mma_rs(float (&d)[64], uint32_t a0, uint32_t a1, uint32_t a2, uint32_t a3, uint64_t db, int sc) {
  asm volatile("{\n.reg .pred p;\nsetp.ne.b32 p, %69, 0;\n"
               "wgmma.mma_async.sync.aligned.m64n128k16.f32.bf16.bf16 " D64 ", {%64,%65,%66,%67}, %68, p, 1, 1, %70;\n}"
               : R8(d, 0), R8(d, 8), R8(d, 16), R8(d, 24), R8(d, 32), R8(d, 40), R8(d, 48), R8(d, 56)
               : "r"(a0), "r"(a1), "r"(a2), "r"(a3), "l"(db), "r"(sc), "n"(TB));
}
#define D128 "{%0,%1,%2,%3,%4,%5,%6,%7,%8,%9,%10,%11,%12,%13,%14,%15,%16,%17,%18,%19,%20,%21,%22,%23,%24,%25,%26,%27,%28,%29,%30,%31," \
             "%32,%33,%34,%35,%36,%37,%38,%39,%40,%41,%42,%43,%44,%45,%46,%47,%48,%49,%50,%51,%52,%53,%54,%55,%56,%57,%58,%59,%60,%61,%62,%63," \
             "%64,%65,%66,%67,%68,%69,%70,%71,%72,%73,%74,%75,%76,%77,%78,%79,%80,%81,%82,%83,%84,%85,%86,%87,%88,%89,%90,%91,%92,%93,%94,%95," \
             "%96,%97,%98,%99,%100,%101,%102,%103,%104,%105,%106,%107,%108,%109,%110,%111,%112,%113,%114,%115,%116,%117,%118,%119,%120,%121,%122,%123,%124,%125,%126,%127}"
#define R128(d, e) R8(d, 0), R8(d, 8), R8(d, 16), R8(d, 24), R8(d, 32), R8(d, 40), R8(d, 48), R8(d, 56), \
                   R8(e, 0), R8(e, 8), R8(e, 16), R8(e, 24), R8(e, 32), R8(e, 40), R8(e, 48), R8(e, 56)
__device__ __forceinline__ void mma256_ss(float (&d)[64], float (&e)[64], uint64_t da, uint64_t db, int sc) {
  asm volatile("{\n.reg .pred p;\nsetp.ne.b32 p, %130, 0;\n"
               "wgmma.mma_async.sync.aligned.m64n256k16.f32.bf16.bf16 " D128 ", %128, %129, p, 1, 1, 0, 1;\n}"
               : R128(d, e) : "l"(da), "l"(db), "r"(sc));
}
__device__ __forceinline__ void mma256_rs(float (&d)[64], float (&e)[64], uint32_t a0, uint32_t a1, uint32_t a2, uint32_t a3, uint64_t db) {
  asm volatile("{\n.reg .pred p;\nsetp.ne.b32 p, 1, 0;\n"
               "wgmma.mma_async.sync.aligned.m64n256k16.f32.bf16.bf16 " D128 ", {%128,%129,%130,%131}, %132, p, 1, 1, 1;\n}"
               : R128(d, e) : "r"(a0), "r"(a1), "r"(a2), "r"(a3), "l"(db));
}
template <int N> __device__ __forceinline__ void keep(float (&a)[N]) {
#pragma unroll
  for (int i = 0; i < N; i++) asm volatile("" : "+f"(a[i])::"memory");
}
template <int N> __device__ __forceinline__ void keep(uint32_t (&a)[N]) {
#pragma unroll
  for (int i = 0; i < N; i++) asm volatile("" : "+r"(a[i])::"memory");
}

#define STAMP(idx) do {} while (0)
#define PROF(grp, cond, idx) do {} while (0)

constexpr float SCL2 = 1.4426950408889634f * 0.08838834764831845f;

__device__ __forceinline__ void pack_p(const float (&s)[64], uint32_t (&p)[32]) {
#pragma unroll
  for (int i = 0; i < 32; i++) p[i] = pack_bf(s[2 * i], s[2 * i + 1]);
}

__device__ __forceinline__ void issue_qk(float (&s)[64], uint32_t q0, uint32_t q1, uint32_t kslot) {
  const uint64_t db = make_desc(kslot, 16, 1024), da0 = make_desc(q0, 16, 1024), da1 = make_desc(q1, 16, 1024);
#pragma unroll
  for (int kk = 0; kk < 8; kk++) mma_ss<0>(s, (kk < 4 ? da0 : da1) + (kk & 3) * 2, db + (kk >> 2) * 1024 + (kk & 3) * 2, kk != 0);
}
__device__ __forceinline__ void issue_pv(float (&o)[64], uint32_t (&p)[32], uint32_t vslot, int acc) {
  uint64_t db = make_desc(vslot, 16384, 1024);
#pragma unroll
  for (int kk = 0; kk < 8; kk++)
    mma_rs<1>(o, p[4 * kk], p[4 * kk + 1], p[4 * kk + 2], p[4 * kk + 3], db + kk * 128, kk == 0 ? acc : 1);
}

template <int H>
__device__ __forceinline__ void store_chunk(const float (&a)[64], uint32_t addr) {
#pragma unroll
  for (int i = 8 * H; i < 8 * H + 8; i += 2)
    stmatrix4(addr ^ ((i & 7) << 4), pack_bf(a[4 * i], a[4 * i + 1]), pack_bf(a[4 * i + 2], a[4 * i + 3]),
              pack_bf(a[4 * i + 4], a[4 * i + 5]), pack_bf(a[4 * i + 6], a[4 * i + 7]));
}
template <int H>
__device__ __forceinline__ void store_chunk(const float (&a)[64], float i0, float i1, uint32_t addr) {
#pragma unroll
  for (int i = 8 * H; i < 8 * H + 8; i += 2)
    stmatrix4(addr ^ ((i & 7) << 4), pack_bf(a[4 * i] * i0, a[4 * i + 1] * i0), pack_bf(a[4 * i + 2] * i1, a[4 * i + 3] * i1),
              pack_bf(a[4 * i + 4] * i0, a[4 * i + 5] * i0), pack_bf(a[4 * i + 6] * i1, a[4 * i + 7] * i1));
}
__device__ __forceinline__ float inv_quad_sum(float l) {
  l += __shfl_xor_sync(0xffffffffu, l, 1);
  l += __shfl_xor_sync(0xffffffffu, l, 2);
  return rcp(l);
}

__device__ __forceinline__ void ln_scalars(float mean, float var, float& mb, float& sd) {
  mb = rbf(mean);
  float r; asm("sqrt.approx.ftz.f32 %0, %1;" : "=f"(r) : "f"(rbf(rbf(var) + 1e-5f)));
  sd = rbf(r);
}

__global__ void __cluster_dims__(2, 1, 1) __launch_bounds__(384, 1) fused_kernel(const __grid_constant__ Maps maps, const Ptrs P) {
  extern __shared__ __align__(1024) uint8_t smem_raw[];
  const uint32_t base = smem_u32(smem_raw);
  const int tid = threadIdx.x, lane = tid & 31;
  const int warp = __shfl_sync(0xffffffffu, tid >> 5, 0);
  const int b = blockIdx.x;
  PROF(31, tid == 0, 0);

  if (b >= NMAIN) {
    float* sc = reinterpret_cast<float*>(smem_raw);
    float* red = sc + DM;
    for (int k = tid; k < DM; k += 384) sc[k] = rbf(silu_f(__bfloat162float(P.c[k])));
    __syncthreads();
    if (tid < 256) {
      const int col = 2048 + (b - NMAIN) * 1024 + (tid & 127) * 8, r0 = (tid >> 7) * 512;
      float acc[8];
#pragma unroll
      for (int e = 0; e < 8; e++) acc[e] = 0.f;
#pragma unroll 1
      for (int r = r0; r < r0 + 512; r += HU) {
        uint4 w[HU];
#pragma unroll
        for (int u = 0; u < HU; u++) w[u] = ldg_stream4(P.w_mod + (size_t)(r + u) * NMOD + col);
#pragma unroll
        for (int u = 0; u < HU; u++) {
          float s = sc[r + u];
          acc[0] += s * bf_lo(w[u].x); acc[1] += s * bf_hi(w[u].x); acc[2] += s * bf_lo(w[u].y); acc[3] += s * bf_hi(w[u].y);
          acc[4] += s * bf_lo(w[u].z); acc[5] += s * bf_hi(w[u].z); acc[6] += s * bf_lo(w[u].w); acc[7] += s * bf_hi(w[u].w);
        }
      }
      if (tid >= 128) {
#pragma unroll
        for (int e = 0; e < 8; e++) red[(tid & 127) * 8 + e] = acc[e];
      }
      const uint32_t tag = ld_relaxed(&g_epoch) % 3 + 1;
      bar_sync(1, 256);
      if (tid < 128) {
        uint32_t o[8];
#pragma unroll
        for (int e = 0; e < 8; e++) o[e] = __float_as_uint(rbf(acc[e] + red[tid * 8 + e])) | tag;
        st_relaxed4(g_mod + col, o[0], o[1], o[2], o[3]);
        st_relaxed4(g_mod + col + 4, o[4], o[5], o[6], o[7]);
        const uint4 wr = ldg_nc4(P.w_r + tid * 8);
        const uint32_t wv[4] = {wr.x, wr.y, wr.z, wr.w};
        float dsum = 0.f;
#pragma unroll
        for (int e = 0; e < 8; e++) {
          const float m = bf_hi(o[e]);
          dsum += (b == NMAIN + 2 ? rbf(1.f + m) : m) * ((e & 1) ? bf_hi(wv[e >> 1]) : bf_lo(wv[e >> 1]));
        }
#pragma unroll
        for (int k = 16; k > 0; k >>= 1) dsum += __shfl_xor_sync(0xffffffffu, dsum, k);
        if (lane == 0) st_relaxed(g_mod + (b - NMAIN) * 4 + warp, tagf(dsum, tag));
      }
    }
    PROF(2, tid == 0, 1);
    return;
  }

  const int rank = b & 1;
  const int rb = ((b >> 4) << 1) | rank, cj = (b >> 1) & 7;
  const uint32_t bfull = base + OFF_BAR, bempty = bfull + NSLOT * 8;
  const uint32_t gfull = bempty + NSLOT * 8, gempty = gfull + 32;
  const uint32_t bar_ofull = gempty + 32;
  const uint32_t bar_ofree = bar_ofull + 32;
  const uint32_t bar_par = bar_ofree + 32;
  const uint32_t bar_mod = bar_par + 8;
  const uint32_t bar_pread = bar_mod + 8;
  const uint32_t bar_xres = bar_pread + 8;
  const uint32_t bar_ring = bar_xres + 8;
  const uint32_t bar_box = bar_ring + 24;
  const uint32_t bar_go = bar_box + 96;
  const uint32_t bar_go2 = bar_go + 16;
  const uint32_t bar_cnt = bar_go + 24;
  const uint32_t xfull = bar_go + 32, xempty = xfull + 32;
  const uint32_t bar_hw = xempty + 32, bar_hx = bar_hw + 8;
  const uint32_t bar_hpub = bar_hx + 16;
  const uint32_t bar_win = bar_hpub + 8;
  const uint32_t bar_rx = bar_win + 8;
  const uint32_t bar_sel = bar_rx + 8;
  const uint32_t bar_gate = bar_sel + 8;
  const uint32_t bar_rel = bar_gate + 8;
  const uint32_t bar_od = bar_rel + 8;
  const uint32_t bar_res = bar_go + 8;
  const uint32_t stage = base + OFF_STAGE, par = base + OFF_PAR;

  if (warp == 8 && elect_one()) {
    for (int s = 0; s < NSLOT; s++) { mbar_init(bfull + s * 8, 1); mbar_init(bempty + s * 8, 16); }
    for (int s = 0; s < 4; s++) { mbar_init(gfull + s * 8, 1); mbar_init(gempty + s * 8, 16); mbar_init(xfull + s * 8, 1); mbar_init(xempty + s * 8, 8); mbar_init(bar_ofree + s * 8, 1); mbar_init(bar_ofull + s * 8, 128); }
    mbar_init(bar_par, 64); mbar_init(bar_mod, 256); mbar_init(bar_pread, 8); mbar_init(bar_xres, 1);
    mbar_init(bar_ring, 8); mbar_init(bar_ring + 8, 8); mbar_init(bar_ring + 16, 8);
    mbar_init(bar_go, 1); mbar_init(bar_go2, 1); mbar_init(bar_cnt, 1); mbar_init(bar_hpub, 8); mbar_init(bar_res, 1); mbar_init(bar_win, 1); mbar_init(bar_rx, 1); mbar_init(bar_sel, 64); mbar_init(bar_gate, 8); mbar_init(bar_rel, 8); mbar_init(bar_od, 1);
    for (int s = 0; s < 12; s++) mbar_init(bar_box + s * 8, 1);
    asm volatile("fence.mbarrier_init.release.cluster;" ::: "memory");
    prefetch_map(&maps.x); prefetch_map(&maps.wq); prefetch_map(&maps.k); prefetch_map(&maps.v);
  }
  if (warp == 9 && elect_one()) {
    mbar_init(bar_hw, 1); mbar_init(bar_hx, 1); mbar_init(bar_hx + 8, 1);
    asm volatile("fence.mbarrier_init.release.cluster;" ::: "memory");
    mbar_expect_tx(bar_hw, 32768);
    mbar_expect_tx(bar_hx, 16384);
    mbar_expect_tx(bar_hx + 8, 16384);
    const __nv_bfloat16* xs = P.x + (size_t)(rb * 128 + cj * 16) * DM;
    bulk_load(base + 2 * GST_BYTES, xs, 16384, bar_hx);
    tma2d(stage, &maps.wm, (b >> 1) * 32, rank * 512, bar_hw);
    tma2d(stage + 16384, &maps.wm, (b >> 1) * 32, rank * 512 + 256, bar_hw);
    bulk_load(base + 3 * GST_BYTES, xs + 8 * DM, 16384, bar_hx + 8);
  }
  cluster_arrive();

  if (warp >= 8) {
    asm volatile("setmaxnreg.dec.sync.aligned.u32 40;");
    if (warp < 10) bar_arrive(1, 320);
    const uint32_t epoch = ld_relaxed(&g_epoch);
    cluster_wait();
    if (warp == 8) {
      const int kvrow = (cj >> 1) * SK + (SK - WIN);
      int wch = cj * 8 + rank * 2;
#pragma unroll 1
      for (int ps = 0; ps < 3; ps++) {
        const CUtensorMap* mw = ps == 2 ? &maps.wo : &maps.wq;
        const uint32_t xt = ps == 1 ? XT1 : XT2, wt = ps == 0 ? WT0 : (ps == 1 ? WT1 : WT2);
        const int nst = ps == 2 ? 32 : 16;
#pragma unroll 1
        for (int i = 0; i < nst; i++) {
          const uint32_t bf = gfull + (i & 3) * 8;
          const int kt = ps == 2 ? (((cj & 1) * 4 + ((i >> 1) & 3)) * 4 + (i >> 3)) * 2 + (i & 1) : (i + (ps ? 0 : b & 14)) & 15;
          const uint32_t wd = base + unit_of(wt, i & 3) + rank * UNIT, xd = base + unit_of(xt, i & 3);
          const uint8_t* xs = g_act + (uint32_t)(rb * 80 + (ps - 1) * 16 + kt) * UNIT;
          if (ps == 0 && i == HD) mbar_wait(bar_mod, 0);
          if (ps == 2 && (i & 15) == 0) mbar_wait(i ? bar_cnt : bar_ofree + 24, 0);
          if ((i & 15) == 0) fence_async();
          if (ps && i == 2) mbar_wait(bar_ofree + (ps - 1) * 16, 0);
          mbar_wait(gempty + (i & 3) * 8, ((i >> 2) & 1) ^ 1);
          if (elect_one()) {
            mbar_expect_tx(bf, ps ? GST_BYTES : 2 * UNIT);
            if (i == 31) bulk_load(xd, xs, UNIT, bf); else if (ps) bulk_load_stream(xd, xs, UNIT, bf);
          }
          if (ps && i < 4) mbar_wait(bempty + i * 8, 1);
          if (elect_one()) {
            tma3d_mc<true>(wd, mw, 0, (i == 31 ? kt ^ (rank * 32) : kt) * 64, i == 31 ? cj * 2 : wch, bf);
            if (ps) {
              mbar_arrive_pred(bar_go, i == GOST - 1);
              mbar_arrive_pred(bar_od, i == ODS);
              mbar_arrive_pred(bar_go2, ps * 16 + i == PG0);
              mbar_arrive_pred(bar_res, ((1u << RES0 | 1u << RES1) >> i) & 1);
              if (ps == 2 && b < NFFN && i >= PD0 && i < PD0 + 16)
                asm volatile("cp.async.bulk.prefetch.L2.global [%0], 4096;" ::"l"(P.w_down + (size_t)b * 32768 + (i - PD0) * 2048) : "memory");
            }
          }
        }
        if (ps == 2) break;
        wch = ps ? ((wch >> 3) ^ rank) * 2 : wch + 4;
#pragma unroll 1
        for (int u = 0; u < 16; u++) {
          const bool isk = (u == 0) || ((u & 1) && u < 15);
          const int blk = (isk ? (u + 1) >> 1 : (u == 15 ? 7 : (u >> 1) - 1)) & 3;
          const uint32_t sl = base + unit_of(ps ? AT1 : AT0, u & 3) + rank * UNIT, bf = bfull + (u & 3) * 8;
          if (u < 4) mbar_wait(gempty + ((u + 1) >> 1) * 8, 1);
          mbar_wait(bempty + (u & 3) * 8, ((u >> 2) & 1) ^ 1);
          if (elect_one()) {
            mbar_expect_tx(bf, SLOT_BYTES);
            tma3d_mc<false>(sl, isk ? &maps.k : &maps.v, 0, kvrow + blk * 128, rank, bf);
            if (ps && u >= PF2T && u < PF2T + 2 * PF2 && !((u - PF2T) & 1))
              tma3d_prefetch(&maps.wo, 0, ((((cj & 1) * 4 + (b >> 5)) * 4 + ((u - PF2T) >> 1)) * 2 + ((b >> 4) & 1)) * 64, (cj ^ rank) * 2);
          }
        }
      }
      if (elect_one()) mbar_expect_tx(bar_rx, UNIT);
      mbar_wait(bar_rel, 0);
      if (elect_one()) {
        bulk_load_stream(base + UNIT, g_act + (uint32_t)(rb * 80 + 16 + 63 - (cj & 1) * 32) * UNIT, UNIT, bar_rx);
      }
      if (b < NFFN) {
#pragma unroll 1
        for (int u = 0; u < 12; u++) {
          const uint32_t dst = base + unit_of(u < 4 ? FT_G : (u < 8 ? FT_U : FT_D), u & 3);
          if (elect_one()) mbar_expect_tx(bar_box + u * 8, UNIT);
          if (u == FB0 || u == 2 || u == FB2) mbar_wait(bar_ring + (u == FB2 ? 16 : (u + 6) & 8), 0);
          if (u >= FPACE) mbar_wait(bar_box + (u - FPACE) * 8, 0);
          if (elect_one()) {
            if (u < 8) tma2d(dst, u < 4 ? &maps.wg : &maps.wu, b * 32, (u & 3) * 256, bar_box + u * 8);
            else tma3d(dst, &maps.wd, 0, b * 32, (u - 8) * 4, bar_box + u * 8);
          }
        }
      }
    } else if (warp == 9) {
      const uint32_t target = 8 * (epoch + 1);
#pragma unroll 1
      for (int i = 0; i < 16; i++) {
        if (i == HDX) mbar_wait(bar_mod, 0);
        if (i == NRS) {
          wait_counter(&g_cnt_h[rb * 32], target);
          PROF(1, lane == 0, 26);
          fence_async();
        }
        mbar_wait(xempty + (i & 3) * 8, ((i >> 2) & 1) ^ 1);
        if (elect_one()) {
          mbar_expect_tx(xfull + (i & 3) * 8, UNIT);
          if (i < NRS) tma2d(base + (i & 3) * GST_BYTES, &maps.x, ((2 * cj + i) & 15) * 64, rb * 128, xfull + (i & 3) * 8);
          else bulk_load_stream(base + (i & 3) * GST_BYTES, g_act + (uint32_t)(rb * 80 + ((2 * cj + i) & 15)) * UNIT, UNIT, xfull + (i & 3) * 8);
        }
      }
      prefetch_map(&maps.wo);
#pragma unroll 1
      for (int t = 0; t < 4; t++) {
        if (t & 1) mbar_wait(bar_od, t >> 1);
#pragma unroll 1
        for (int p = 0; p < 32768 / OPS; p++) {
          const uint32_t w = p / (16384 / OPS), c = (p / (8192 / OPS)) & 1, off = w * 8192 + (p % (8192 / OPS)) * OPS;
          mbar_wait(bar_ofull + (t & 1) * 16 + w * 8, t >> 1);
          if (elect_one()) {
            bulk_store(g_act + (uint32_t)(rb * 80 + 16 + (cj * 4 + t) * 2 + c) * UNIT + off, base + unit_of(QT, 2 * t + c) + off, OPS);
            asm volatile("cp.async.bulk.commit_group;" ::: "memory");
            asm volatile("cp.async.bulk.wait_group.read %0;" ::"n"(OFL) : "memory");
          }
        }
        if (elect_one()) {
          asm volatile("cp.async.bulk.wait_group.read 0;" ::: "memory");
          mbar_arrive_pred(bar_ofree + t * 8, t < 3);
          asm volatile("cp.async.bulk.wait_group 0;" ::: "memory");
          fence_async();
          red_release(&g_cnt_o[((rb * 4 + t) * 2 + (cj >> 2)) * 32], 2);
        }
        if (t & 1) {
          wait_counter(&g_cnt_o[(rb * 8 + 2 * t - 2 + (cj & 1)) * 32], target);
          wait_counter(&g_cnt_o[(rb * 8 + 2 * t + (cj & 1)) * 32], target);
          if (elect_one()) mbar_arrive_pred(bar_ofree + 24, t == 1);
        }
      }
      wait_counter(&g_cnt_o[(rb * 8 + 7 - (cj & 1)) * 32], target);
      fence_async();
      if (elect_one()) {
        mbar_arrive(bar_cnt);
        PROF(2, true, 27);
        mbar_expect_tx(bar_xres, 32768);
      }
#pragma unroll 1
      for (int u = 0; u < 2; u++) {
        mbar_wait(bar_res, u);
        if (elect_one()) tma2d(base + OFF_RES + u * UNIT, &maps.x, cj * 128 + u * 64, rb * 128, bar_xres);
      }
      const uint32_t tag = epoch % 3 + 1;
      const uint32_t* inbox = g_cand + (lane & 15);
      mbar_wait(bar_ring + 16, 0);
      uint32_t c0 = ld_relaxed(inbox), n = 0;
#define CAND_STEP(cv)                                                                                        \
      {                                                                                                      \
        const bool valid = (cv & 3u) == tag, all = __all_sync(0xffffffffu, valid);                           \
        const uint32_t best = __reduce_max_sync(0xffffffffu, valid ? cv : 0u);                               \
        const uint32_t blk = __ffs(__ballot_sync(0xffffffffu, cv == best)) - 1;                              \
        if (best) sts2(par + PAR_CONST + 56, best, (blk << 7 | (~best >> 2 & 127)) | (all ? 0x1800 : 0x800)); \
        if (all) break;                                                                                      \
        cv = ld_relaxed(inbox);                                                                              \
      }
      while (true) { CAND_STEP(c0) watchdog(n); }
    } else {
      const int t2 = tid - 320;
      if (t2 == 0) {
        mbar_wait(bar_hpub, 0);
        PROF(1, true, 24);
        red_release(&g_cnt_h[rb * 32], 1);
        PROF(1, true, 25);
        prefetch_map(&maps.wg); prefetch_map(&maps.wu); prefetch_map(&maps.wd); prefetch_map(&maps.out);
      }
      __syncwarp();
      if (b < NFFN) {
        mbar_wait(bar_go2, 0);
        const __nv_bfloat16* pg = ((b & 1) ? P.w_up : P.w_gate) + (b >> 1) * 64 + (size_t)t2 * FF;
        const __nv_bfloat16* pd = P.w_down + (size_t)b * 32768 + t2 * 64;
        PROF(2, t2 == 0, 13);
#pragma unroll 1
        for (int i = 0; i < WN; i += WB) {
          uint32_t v[WB];
#pragma unroll
          for (int u = 0; u < WB; u++)
            asm volatile("ld.global.cg.L2::128B.u32 %0, [%1];" : "=r"(v[u]) : "l"(i < 16 ? pg + (size_t)(i + u) * 64 * FF : pd + (i + u - 16) * 4096));
#pragma unroll
          for (int u = 1; u < WB; u++) v[0] ^= v[u];
          sts1(par + PAR_SINK + t2 * 4, v[0]);
        }
        PROF(2, t2 == 0, 14);
      }
      const uint32_t tag = epoch % 3 + 1;
      mbar_wait(bar_go, 0);
      if (warp == 10) {
        const uint32_t* src = g_mod + 2 * DM + cj * 128 + lane * 4;
        const uint2 wr = *reinterpret_cast<const uint2*>(P.w_r + cj * 128 + lane * 4);
        uint4 vga, vsb, vcb, vgb;
        uint32_t n = 0;
        do {
          vga = ld_relaxed4(src); vsb = ld_relaxed4(src + DM); vcb = ld_relaxed4(src + 2 * DM); vgb = ld_relaxed4(src + 3 * DM);
          watchdog(n);
        } while (!(tag_ok(vga, tag) && tag_ok(vsb, tag) && tag_ok(vcb, tag) && tag_ok(vgb, tag)));
        const float c0 = rbf(1.f + bf_hi(vcb.x)), c1 = rbf(1.f + bf_hi(vcb.y)), c2 = rbf(1.f + bf_hi(vcb.z)), c3 = rbf(1.f + bf_hi(vcb.w));
        const float a0 = c0 * bf_lo(wr.x), a1 = c1 * bf_hi(wr.x), a2 = c2 * bf_lo(wr.y), a3 = c3 * bf_hi(wr.y);
        const uint32_t h0 = pack_bf(a0, a1), h1 = pack_bf(a2, a3);
        const uint32_t t1 = par + PAR_T1 + (lane >> 2) * 64 + (lane & 1) * 32 + (lane & 2) * 2;
        sts1(t1, h0); sts1(t1 + 8, pack_bf(a0 - bf_lo(h0), a1 - bf_hi(h0)));
        sts1(t1 + 16, h1); sts1(t1 + 24, pack_bf(a2 - bf_lo(h1), a3 - bf_hi(h1)));
        sts4(par + PAR_T2 + lane * 32, make_uint4(pack_bf(c0, c1), __byte_perm(vsb.x, vsb.y, 0x7632), __byte_perm(vgb.x, vgb.y, 0x7632), __byte_perm(vga.x, vga.y, 0x7632)));
        sts4(par + PAR_T2 + lane * 32 + 16, make_uint4(pack_bf(c2, c3), __byte_perm(vsb.z, vsb.w, 0x7632), __byte_perm(vgb.z, vgb.w, 0x7632), __byte_perm(vga.z, vga.w, 0x7632)));
      } else if (lane < 4) {
        const uint4 g = poll4(lane < 2 ? g_mod + 5 * DM + b * 8 + lane * 4 : g_mod + 16 - lane * 4, tag);
        sts1(par + PAR_CONST + 60, 0);
        if (lane < 2) sts4(par + PAR_CONST + 16 + lane * 16, g);
        else sts2(par + PAR_CONST + (lane - 2) * 8, __float_as_uint(untag_sum(g.x, g.y) + untag_sum(g.z, g.w)), epoch);
      }
      __syncwarp();
#pragma unroll 4
      for (int q = XR; q < XE; q++) st_b128(g_xch + ((size_t)b * 8 * 256 + q * 64 + t2) * 4, (epoch & 1) << 16, 0, 0, 0);
      for (int q = 0; q < 2; q++) st_relaxed4(g_stats + ((size_t)cj * SEQ + rb * 128 + q * 64 + t2) * 4, 0, 0, 0, 0);
      if (b < NFFN)
        for (int q = 0; q < 4; q++) st_relaxed4(g_ypart + ((size_t)(q * 32 + (t2 >> 1)) * NFFN + b) * 8 + (t2 & 1) * 4, 0, 0, 0, 0);
      st_relaxed4(g_row + rb * 2 * DM + (t2 >> 5) * DM + cj * 128 + (t2 & 31) * 4, 0, 0, 0, 0);
      __threadfence();
      mbar_arrive(bar_par);
      mbar_wait(bar_gate, 0);
      uint32_t have = 0, n = 0;
      while (true) {
        const uint32_t st = lds1(par + PAR_CONST + 60) >> 7;
        if ((st & 31) != have) {
          const uint32_t* hsrc = g_row + (st & 15) * 2 * DM + t2 * 4;
          uint4 hv[4];
          bool ok = true;
#pragma unroll
          for (int i = 0; i < 4; i++) hv[i] = ld_pairs(hsrc + i * 256);
#pragma unroll
          for (int i = 0; i < 4; i++) {
            sts2(base + ((FT_G >> i * 4) & 15) * UNIT + (warp & 1) * 8192 + 256 + lane * 8, hv[i].x, hv[i].z);
            ok = ok && hv[i].y == tag && hv[i].w == tag;
          }
          have = __all_sync(0xffffffffu, ok) ? st & 31 : 0;
        }
        if ((st ^ have) == 32) break;
        watchdog(n);
      }
      mbar_arrive(bar_sel);
    }
    __syncwarp();
    cluster_arrive();
    {
      const uint32_t tag = epoch % 3 + 1, t3 = tid - 256;
      mbar_wait(bar_win, 0);
      uint2 win = lds2(par + PAR_CONST + 56);
      win.y &= 0x7ff;
      const uint32_t* fsrc = g_row + (win.y >> 7) * 2 * DM + (b >> 1) * 16 + (t3 & 3) * 4 + (b & 1) * 2;
      const uint32_t* ysrc = g_ypart + (size_t)b * NFFN * 8 + min(t3, NFFN - 1) * 4;
      uint2 fh = ld_pair(fsrc), fx = ld_pair(fsrc + DM);
      if (PSL) __nanosleep(PSL);
      uint4 ya = ld_relaxed4(ysrc), yb = ld_relaxed4(ysrc + NFFN * 4);
      const float rwin = __uint_as_float(((int)win.x < 0 ? win.x & 0x7fffffffu : ~win.x) & ~0x1ffu);
      const float rs = rbf(rcp(1.f + __expf(-rbf(rwin))));
      uint32_t n = 0;
      while (fh.y != tag || fx.y != tag) { fh = ld_pair(fsrc); fx = ld_pair(fsrc + DM); watchdog(n); }
      while (!(tag_ok(ya, tag) && tag_ok(yb, tag))) {
        if (!tag_ok(ya, tag)) ya = ld_relaxed4(ysrc);
        if (!tag_ok(yb, tag)) yb = ld_relaxed4(ysrc + NFFN * 4);
        watchdog(n);
      }
      __syncwarp();
      PROF(8, t3 == 0, 5);
      float y0 = untag_sum(ya.x, yb.x), y1 = untag_sum(ya.y, yb.y), y2 = untag_sum(ya.z, yb.z), y3 = untag_sum(ya.w, yb.w);
      const bool u1 = lane & 2, u2 = lane & 4;
      y0 = (u1 ? y2 : y0) + __shfl_xor_sync(0xffffffffu, u1 ? y0 : y2, 2);
      y1 = (u1 ? y3 : y1) + __shfl_xor_sync(0xffffffffu, u1 ? y1 : y3, 2);
      y0 = (u2 ? y1 : y0) + __shfl_xor_sync(0xffffffffu, u2 ? y0 : y1, 4);
      y0 += __shfl_xor_sync(0xffffffffu, y0, 8);
      if (!(lane & 8)) sts1(par + PAR_RED + 64 + (t3 >> 4) * 32 + ((lane & 1) * 4 + (lane & 2) + ((lane >> 2) & 1)) * 4, __float_as_uint(y0));
      bar_sync(4, 128);
      if (t3 < 4) {
        y0 = 0.f; y1 = 0.f;
#pragma unroll
        for (int w4 = 0; w4 < 7; w4++) {
          const uint2 v = lds2(par + PAR_RED + 64 + w4 * 32 + t3 * 8);
          y0 += __uint_as_float(v.x); y1 += __uint_as_float(v.y);
        }
        const uint2 gv = lds2(par + PAR_CONST + 16 + t3 * 8);
        const uint32_t upd = hmul2(pack_bf(y0, y1), pack_bf(rs, rs));
        *reinterpret_cast<uint32_t*>(P.out + (size_t)win.y * DM + b * 8 + t3 * 2) =
            hadd2(fx.x, hmul2(__byte_perm(gv.x, gv.y, 0x7632), hadd2(fh.x, upd)));
        if (b == 0 && t3 == 0) st_relaxed(&g_epoch, epoch + 1);
      }
      PROF(31, t3 == 0, 36);
    }
    cluster_wait();
  } else {
    const int wg = warp >> 2;

    uint32_t tag;
    {
      uint32_t* const pmod = g_modp + rank * 2 * DM + (b >> 1) * 32 + lane;
      uint32_t* const pln = g_ln1 + (rb * 128 + cj * 16 + warp) * 4;
      const uint32_t cv = ldg_nc1(P.c + rank * 512 + tid * 2);
      const uint32_t epoch = ld_relaxed(&g_epoch);
      if (warp == 0) st_relaxed(pmod, 0);
      if (lane == 0) { st_relaxed2(pln, 0, 0); st_relaxed2(pln + 32, 0, 0); }
      asm volatile("setmaxnreg.inc.sync.aligned.u32 232;");
      sts1(par + tid * 4, pack_bf(silu_f(bf_lo(cv)), silu_f(bf_hi(cv))));
      bar_sync(1, 320);
      tag = epoch % 3 + 1;
#pragma unroll
      for (int part = 0; part < 3; part++) {
        if (part != 1) {
          const uint32_t xa = base + (2 + part / 2) * GST_BYTES + warp * 2048 + lane * 16;
          mbar_wait(bar_hx + part * 4, 0);
          float s0 = 0.f, s1 = 0.f, q0 = 0.f, q1 = 0.f;
#pragma unroll
          for (int q = 0; q < 4; q++) {
            const uint4 xv = lds4(xa + q * 512);
            const uint32_t u[4] = {xv.x, xv.y, xv.z, xv.w};
#pragma unroll
            for (int e = 0; e < 4; e++) { const float lo = bf_lo(u[e]), hi = bf_hi(u[e]); s0 += lo; s1 += hi; q0 += lo * lo; q1 += hi * hi; }
          }
          s0 += s1; q0 += q1;
#pragma unroll
          for (int o = 16; o > 0; o >>= 1) { s0 += __shfl_xor_sync(0xffffffffu, s0, o); q0 += __shfl_xor_sync(0xffffffffu, q0, o); }
          const float mean = s0 * (1.f / DM);
          float mb, sd;
          ln_scalars(mean, fmaxf(q0 * (1.f / DM) - mean * mean, 0.f), mb, sd);
          if (lane == 0) st_relaxed2(pln + part * 16, __float_as_uint(mb) | tag, __float_as_uint(sd) | tag);
          PROF(1, tid == 0 && part == 2, 4);
        } else {
          float acc[8];
#pragma unroll
          for (int e = 0; e < 8; e++) acc[e] = 0.f;
          const uint32_t wa = stage + (tid >> 2) * 64 + (((tid ^ (tid >> 3)) & 3) << 4), sa = par + (tid >> 3) * 4, sh = (tid & 4) ? 0x3244 : 0x1044;
          mbar_wait(bar_hw, 0);
#pragma unroll
          for (int p = 0; p < 8; p++) {
            const uint4 w = lds4(wa + p * 4096);
            const float s = __uint_as_float(__byte_perm(lds1(sa + p * 128), 0, sh));
            acc[0] += s * bf_lo(w.x); acc[1] += s * bf_hi(w.x); acc[2] += s * bf_lo(w.y); acc[3] += s * bf_hi(w.y);
            acc[4] += s * bf_lo(w.z); acc[5] += s * bf_hi(w.z); acc[6] += s * bf_lo(w.w); acc[7] += s * bf_hi(w.w);
          }
#pragma unroll
          for (int e = 0; e < 4; e++) {
            const bool up = lane & 16;
            acc[e] = (up ? acc[e + 4] : acc[e]) + __shfl_xor_sync(0xffffffffu, up ? acc[e] : acc[e + 4], 16);
          }
#pragma unroll
          for (int e = 0; e < 2; e++) {
            const bool up = lane & 8;
            acc[e] = (up ? acc[e + 2] : acc[e]) + __shfl_xor_sync(0xffffffffu, up ? acc[e] : acc[e + 2], 8);
          }
          {
            const bool up = lane & 4;
            acc[0] = (up ? acc[1] : acc[0]) + __shfl_xor_sync(0xffffffffu, up ? acc[0] : acc[1], 4);
          }
          sts1(par + 1024 + warp * 128 + ((lane & 3) * 8 + (lane >> 2)) * 4, __float_as_uint(acc[0]));
          bar_sync(1, 256);
          if (warp == 0) {
            float s = 0.f;
#pragma unroll
            for (int w8 = 0; w8 < 8; w8++) s += __uint_as_float(lds1(par + 1024 + w8 * 128 + lane * 4));
            st_relaxed(pmod, (__float_as_uint(s) & ~3u) | tag);
          }
          PROF(1, tid == 0, 3);
        }
      }
      {
        uint2 s0 = ld_relaxed2(g_ln1 + (rb * 128 + (tid & 127)) * 4);
        uint4 v[4];
#pragma unroll
        for (int q = 0; q < 4; q++) v[q] = ld_relaxed4(g_modp + q * DM + tid * 4);
        {
          uint32_t n = 0;
          while (!(tag_ok(v[0], tag) && tag_ok(v[1], tag) && tag_ok(v[2], tag) && tag_ok(v[3], tag))) {
#pragma unroll
            for (int q = 0; q < 4; q++)
              if (!tag_ok(v[q], tag)) v[q] = ld_relaxed4(g_modp + q * DM + tid * 4);
            if (((s0.x ^ tag) | (s0.y ^ tag)) & 3u) s0 = ld_relaxed2(g_ln1 + (rb * 128 + (tid & 127)) * 4);
            watchdog(n);
          }
        }
        const uint32_t d = stage + (tid >> 2) * 64 + (tid & 1) * 32 + (tid & 2) * 2;
        sts1(d, pack_bf(1.f + rbf(untag_sum(v[1].x, v[3].x)), 1.f + rbf(untag_sum(v[1].y, v[3].y))));
        sts1(d + 16, pack_bf(1.f + rbf(untag_sum(v[1].z, v[3].z)), 1.f + rbf(untag_sum(v[1].w, v[3].w))));
        sts1(d + 8, pack_bf(untag_sum(v[0].x, v[2].x), untag_sum(v[0].y, v[2].y)));
        sts1(d + 24, pack_bf(untag_sum(v[0].z, v[2].z), untag_sum(v[0].w, v[2].w)));
        if (wg == 0) {
          uint32_t n = 0;
          while (((s0.x ^ tag) | (s0.y ^ tag)) & 3u) { s0 = ld_relaxed2(g_ln1 + (rb * 128 + tid) * 4); watchdog(n); }
          uint32_t ih, il;
          split_inv(bf_hi(s0.y), ih, il);
          sts4(stage + 4096 + tid * 16, make_uint4(__byte_perm(s0.x, 0, 0x3232), ih, il, 0));
        }
        mbar_arrive(bar_mod);
      }
      cluster_wait();
      if (wg == 1) bar_arrive(2, 256);
      mbar_wait(bar_mod, 0);
      PROF(1, tid == 0, 2);
    }

    float f0 = 0.f, f1 = 0.f;
    const uint32_t rempty = lane < 2 ? mapa(bempty, lane & 1) : 0;
    constexpr uint32_t GE = NSLOT * 8 + 32;
    float o[64], s[64];
#pragma unroll 1
    for (int ps = 0; ps < 3; ps++) {
      {
        const uint32_t xt = ps == 1 ? XT1 : XT2, wt = ps == 1 ? WT1 : WT2;
        const int nst = ps == 2 ? 28 : 14;
        if (ps == 0) {
          float ga[64], gb[64];
#pragma unroll
          for (int i = 0; i < 64; i++) { ga[i] = 0.f; gb[i] = 0.f; }
          uint32_t a[2][16];
          const uint32_t l = fresh_lane();
          const uint4 r0 = lds4(stage + 4096 + (warp * 16 + (l >> 2)) * 16), r1 = lds4(stage + 4096 + 128 + (warp * 16 + (l >> 2)) * 16);
          auto transform = [&](int i, uint32_t (&f)[16], uint32_t z) {
            const uint32_t ad = base + (i & 3) * GST_BYTES + wg * 8192 + frag_offset(warp) + z;
            mbar_wait(xfull + (i & 3) * 8, i >> 2);
#pragma unroll
            for (int kk = 0; kk < 4; kk++) ldmatrix4(ad ^ (kk * 32), f[4 * kk], f[4 * kk + 1], f[4 * kk + 2], f[4 * kk + 3]);
#pragma unroll
            for (int kk = 0; kk < 4; kk++) {
              const uint4 m = lds4(stage + (l & 3) * 16 + ((2 * cj + i) & 15) * 256 + kk * 64);
              f[4 * kk] = ln_mod(f[4 * kk], r0.x, r0.y, r0.z, m.x, m.z);
              f[4 * kk + 1] = ln_mod(f[4 * kk + 1], r1.x, r1.y, r1.z, m.x, m.z);
              f[4 * kk + 2] = ln_mod(f[4 * kk + 2], r0.x, r0.y, r0.z, m.y, m.w);
              f[4 * kk + 3] = ln_mod(f[4 * kk + 3], r1.x, r1.y, r1.z, m.y, m.w);
            }
            keep(f);
            mbar_arrive_pred(xempty + (i & 3) * 8, l == 0);
          };
          auto publish = [&](int u, uint32_t (&f)[16]) {
            const uint32_t sc = stage + 8192 + wg * 8192;
#pragma unroll
            for (int kk = 0; kk < 4; kk++) stmatrix4((sc + frag_offset(warp)) ^ (kk * 32), f[4 * kk], f[4 * kk + 1], f[4 * kk + 2], f[4 * kk + 3]);
            __syncwarp();
            const uint32_t src = sc + (warp & 3) * 2048 + l * 16;
            uint8_t* dst = g_act + (uint32_t)(rb * 80 + cj * 2 + u) * UNIT + warp * 2048 + l * 16;
#pragma unroll
            for (int p4 = 0; p4 < 4; p4++) stg4(dst + p4 * 512, lds4(src + p4 * 512));
            __syncwarp();
            if (u == 1) mbar_arrive_pred(bar_hpub, l == 0);
          };
          auto multiply = [&](int i, uint32_t (&f)[16]) {
            mbar_wait(gfull + (i & 3) * 8, i >> 2);
            const uint64_t db = make_desc(base + (i & 3) * GST_BYTES + UNIT, 8192, 1024);
            wg_fence();
#pragma unroll
            for (int kk = 0; kk < 4; kk++) mma256_rs(ga, gb, f[4 * kk], f[4 * kk + 1], f[4 * kk + 2], f[4 * kk + 3], db + kk * 128);
            wg_commit();
          };
          transform(0, a[0], 0); publish(0, a[0]); transform(1, a[1], 0); multiply(0, a[0]); publish(1, a[1]);
#pragma unroll
          for (int i = 1; i < NRS; i++) {
            if (i >= 2) {
              uint32_t z = r0.w;
#pragma unroll
              for (int k = 0; k < 16; k += 2) asm volatile("lop3.b32 %0, %1, %2, %0, 0xA8;" : "+r"(z) : "r"(a[i & 1][k]), "r"(a[i & 1][k + 1]));
              transform(i, a[i & 1], z);
            }
            multiply(i, a[i & 1]);
            wg_wait<1>();
            mbar_arrive_cl(rempty, GE + ((i + 3) & 3) * 8);
          }
          mbar_arrive_pred(bar_pread, l == 0);
#pragma unroll 1
          for (int i = NRS; i < 14; i++) {
            mbar_wait(xfull + (i & 3) * 8, (i >> 2) & 1);
            mbar_wait(gfull + (i & 3) * 8, (i >> 2) & 1);
            const uint32_t xa = base + (i & 3) * GST_BYTES;
            const uint64_t da = make_desc(xa + wg * 8192, 16, 1024), db = make_desc(xa + UNIT, 8192, 1024);
            if (i == 13) bar_sync(2 + wg, 256);
            wg_fence();
#pragma unroll
            for (int kk = 0; kk < 4; kk++) mma256_ss(ga, gb, da + kk * 2, db + kk * 128, 1);
            wg_commit();
            if (i == 13) bar_arrive(3 - wg, 256);
            wg_wait<1>();
            uint32_t z = r0.w;
#pragma unroll
            for (int k = 0; k < 16; k += 2) asm volatile("lop3.b32 %0, %1, %2, %0, 0xA8;" : "+r"(z) : "r"(a[1][k]), "r"(a[1][k + 1]));
            mbar_arrive_cl(rempty, GE + ((i + 3) & 3) * 8 + z);
            mbar_arrive_pred(xempty + ((i + 3) & 3) * 8, l == 0 && i != NRS);
          }
          mbar_wait(xfull + 16, 1);
          mbar_wait(xfull + 24, 1);
          wg_wait<0>();
          keep(ga); keep(gb);
#pragma unroll
          for (int i = 0; i < 64; i++) {
            asm volatile("mov.b32 %0, %1;" : "=f"(s[i]) : "f"(ga[i]));
            asm volatile("mov.b32 %0, %1;" : "=f"(o[i]) : "f"(gb[i]));
          }
        } else {
          float ga[64], gb[64];
#pragma unroll
          for (int i = 0; i < 64; i++) {
            asm volatile("mov.b32 %0, %1;" : "=f"(ga[i]) : "f"(s[i]));
            asm volatile("mov.b32 %0, %1;" : "=f"(gb[i]) : "f"(o[i]));
          }
#pragma unroll 1
          for (int i = 0; i < nst; i++) {
            mbar_wait(gfull + (i & 3) * 8, (i >> 2) & 1);
            const uint64_t da = make_desc(base + unit_of(xt, i & 3) + wg * 8192, 16, 1024), db = make_desc(base + unit_of(wt, i & 3), 8192, 1024);
            if (i == nst - 1) bar_sync(2 + wg, 256);
            wg_fence();
#pragma unroll
            for (int kk = 0; kk < 4; kk++) mma256_ss(ga, gb, da + kk * 2, db + kk * 128, kk ? 1 : i);
            wg_commit();
            if (i == nst - 1) bar_arrive(3 - wg, 256);
            wg_wait<1>();
            mbar_arrive_cl(rempty, GE + ((i + 3) & 3) * 8, i != 0);
            PROF(4, tid == 0 && (i & 3) == 0, 40 + (ps - 1) * 4 + i / 4);
          }
          wg_wait<0>();
          keep(ga); keep(gb);
#pragma unroll
          for (int i = 0; i < 64; i++) {
            asm volatile("mov.b32 %0, %1;" : "=f"(s[i]) : "f"(ga[i]));
            asm volatile("mov.b32 %0, %1;" : "=f"(o[i]) : "f"(gb[i]));
          }
        }
        mbar_arrive_cl(rempty, GE + (ps == 2 ? 24 : 8));
        if (ps == 2) break;
      }
      const uint32_t qw = base + wg * 8192, qt = QT >> (16 * ps), at = ps ? AT1 : AT0;
      {
        const uint32_t wt = ps ? WT1 : WT0;
        const uint64_t da0 = make_desc(qw + unit_of(qt, 2), 16, 1024), da1 = make_desc(qw + unit_of(qt, 3), 16, 1024);
        const uint64_t db0 = make_desc(base + unit_of(wt, 2), 8192, 1024), db1 = make_desc(base + unit_of(wt, 3), 8192, 1024);
        mbar_wait(gfull + 16, 1);
        mbar_wait(gfull + 24, 1);
        bar_sync(2 + wg, 256);
        wg_fence();
#pragma unroll
        for (int kk = 0; kk < 8; kk++) mma_ss<1>(s, (kk < 4 ? da0 : da1) + (kk & 3) * 2, (kk < 4 ? db0 : db1) + (kk & 3) * 128, 1);
        wg_commit();
        bar_arrive(3 - wg, 256);
        mbar_wait(ps == 0 ? bar_pread : bar_ofree + 8, 0);
        mbar_wait(bfull, 0);
        wg_wait<0>();
        keep(s);
        PROF(2, tid == 0, 8 + ps * 8);
        store_chunk<0>(s, qw + unit_of(qt, 0) + frag_offset(warp));
        store_chunk<1>(s, qw + unit_of(qt, 1) + frag_offset(warp));
        fence_async_smem();
        bar_sync(2 + wg, 256);
        wg_fence();
        issue_qk(s, qw + unit_of(qt, 0), qw + unit_of(qt, 1), base + unit_of(at, 0));
        wg_commit();
#pragma unroll
        for (int kk = 0; kk < 8; kk++) mma_ss<1>(o, (kk < 4 ? da0 : da1) + (kk & 3) * 2, (kk < 4 ? db0 : db1) + UNIT / 16 + (kk & 3) * 128, 1);
        wg_commit();
        bar_arrive(3 - wg, 256);
        wg_wait<1>();
        keep(s);
        mbar_arrive_cl(rempty, 0);
      }
      PROF(4, tid == 0 && ps == 1, 61);
      float l0 = 0.25f, l1 = 0.25f;
      auto step = [&](auto odd_c, const int j, uint32_t (&pw)[32], uint32_t (&pr)[32]) {
        constexpr bool ODD = decltype(odd_c)::value;
        const bool first = !ODD && (j & 2) == 0, last = ODD && j == 7;
        const uint32_t ph = (j >> 1) & 1;
        float i0, i1, a0, a1;
        if (first) { i0 = inv_quad_sum(l0); i1 = inv_quad_sum(l1); l0 = 0.f; l1 = 0.f; }
        bool redo = !ODD && (j | ps) == 0, again = false;
        while (true) {
          if (redo) {
            float m0 = fmaxf(s[0], s[1]), m1 = fmaxf(s[2], s[3]);
#pragma unroll
            for (int i = 1; i < 16; i++) { m0 = fmaxf(m0, fmaxf(s[4 * i], s[4 * i + 1])); m1 = fmaxf(m1, fmaxf(s[4 * i + 2], s[4 * i + 3])); }
            m0 = fmaxf(m0, __shfl_xor_sync(0xffffffffu, m0, 1)); m1 = fmaxf(m1, __shfl_xor_sync(0xffffffffu, m1, 1));
            m0 = fmaxf(m0, __shfl_xor_sync(0xffffffffu, m0, 2)); m1 = fmaxf(m1, __shfl_xor_sync(0xffffffffu, m1, 2));
            m0 *= SCL2; m1 *= SCL2;
            if (!first) {
              m0 = fmaxf(m0, f0); m1 = fmaxf(m1, f1);
              const float c0 = ex2(f0 - m0), c1 = ex2(f1 - m1);
              l0 *= c0; l1 *= c1;
              wg_wait<0>();
              keep(o);
#pragma unroll
              for (int i = 0; i < 16; i++) { o[4 * i] *= c0; o[4 * i + 1] *= c0; o[4 * i + 2] *= c1; o[4 * i + 3] *= c1; }
            }
            f0 = m0; f1 = m1;
          }
          float b0 = 0.f, b1 = 0.f;
          a0 = 0.f; a1 = 0.f;
#pragma unroll
          for (int i = 0; i < 16; i++) {
            const float e0 = ex2(fmaf(s[4 * i], SCL2, -f0)), e1 = ex2(fmaf(s[4 * i + 1], SCL2, -f0));
            const float e2 = ex2(fmaf(s[4 * i + 2], SCL2, -f1)), e3 = ex2(fmaf(s[4 * i + 3], SCL2, -f1));
            a0 += e0; b0 += e1; a1 += e2; b1 += e3;
            pw[2 * i] = pack_bf(e0, e1); pw[2 * i + 1] = pack_bf(e2, e3);
            if (i == VREL) {
#pragma unroll
              for (int k = 0; k < 2 * VREL + 2; k++) asm volatile("" : "+r"(pw[k])::"memory");
              mbar_wait(bfull + (ODD ? 24 : 8), ph);
              wg_wait<0>();
              mbar_arrive_cl(rempty, ODD ? 16 : (j ? 0 : GE + 16), !again);
              if (!ODD) mbar_arrive_cl(rempty, GE + 24, !again && j == 0);
#pragma unroll
              for (int k = 4 * VREL + 4; k < 64; k++) asm volatile("" : "+f"(s[k])::"memory");
            }
          }
          a0 += b0; a1 += b1;
          if (redo) break;
          redo = __any_sync(0xffffffffu, !(a0 + a1 < 0x1p70f));
          if (first) {
            uint32_t m0 = __ballot_sync(0xffffffffu, a0 > 0x1p-50f), m1 = __ballot_sync(0xffffffffu, a1 > 0x1p-50f);
            m0 |= m0 >> 1; m1 |= m1 >> 1; m0 |= m0 >> 2; m1 |= m1 >> 2;
            redo = redo || (m0 & m1 & 0x11111111u) != 0x11111111u;
          }
          if (!redo) break;
          again = true;
        }
        l0 += a0; l1 += a1;
        keep(pw);
        keep(o);
        const uint32_t qo = qt >> (j ? 0 : 8);
        if (first) store_chunk<0>(o, i0, i1, qw + unit_of(qo, 0) + frag_offset(warp));
        keep(o);
        bar_sync(2 + wg, 256);
        if (!last) {
          const uint32_t qn = qt >> (j >= 3 ? 8 : 0);
          wg_fence();
          issue_qk(s, qw + unit_of(qn, 0), qw + unit_of(qn, 1), base + unit_of(at, ODD ? 3 : 1));
          wg_commit();
          mbar_wait(bfull + (ODD ? 0 : 16), ODD ? ph ^ 1 : ph);
        }
        if (first) { store_chunk<1>(o, i0, i1, qw + unit_of(qo, 1) + frag_offset(warp)); keep(o); }
        wg_fence();
        issue_pv(o, pw, base + unit_of(at, ODD ? (last ? 3 : 0) : 2), !first);
        wg_commit();
        bar_arrive(3 - wg, 256);
        if (first) { fence_async_smem(); mbar_arrive_pred(bar_ofull + wg * 8, j); PROF(2, tid == 0 && j, 9 + ps * 8); }
        wg_wait<1>();
        keep(s);
        mbar_arrive_cl(rempty, ODD ? 24 : 8, !last);
        PROF(4, tid == 0 && ps == 1, 51 + j);
      };
      uint32_t pa[32], pb[32];
#pragma unroll 1
      for (int j = 0; j < 8; j += 2) {
        step(std::false_type{}, j, pa, pb);
        step(std::true_type{}, j + 1, pb, pa);
      }
      {
        const float i0 = inv_quad_sum(l0), i1 = inv_quad_sum(l1);
        wg_wait<0>();
        keep(o);
        mbar_arrive_cl(rempty, 24);
        store_chunk<0>(o, i0, i1, qw + unit_of(qt, 2) + frag_offset(warp));
        store_chunk<1>(o, i0, i1, qw + unit_of(qt, 3) + frag_offset(warp));
        fence_async_smem();
        mbar_arrive(bar_ofull + 16 + wg * 8);
      }
      PROF(2, tid == 0, 10 + ps * 8);
    }

    const int ln = fresh_lane(), g = ln >> 2, tq = ln & 3, ct = warp * 32 + ln;
    const bool lane0 = ln == 0;
    const int lrow0 = warp * 16 + g;
    const int grow0 = rb * 128 + lrow0;
    const uint32_t res = base + OFF_RES, trow = res + wg * 8192 + frag_offset(warp);
    uint32_t xr[32];
    uint4 sv[4], own;
    uint32_t* sp[4];
#pragma unroll
    for (int k = 0; k < 4; k++) sp[k] = g_stats + ((((tq >> 1) * 4 + k) ^ cj) * SEQ + grow0 + (tq & 1) * 8) * 4;
    {
      const uint64_t da = make_desc(base + wg * 8192, 16, 1024), db = make_desc(base, 8192, 1024);
      constexpr int U = UNIT / 16;
#define HALF_STAGE(acc, xu, wu) _Pragma("unroll") for (int kk = 0; kk < 4; kk++) mma_ss<1>(acc, da + (xu) * U + kk * 2, db + (wu) * U + kk * 128, 1)
      PROF(10, ct == PT, 19); STAMP(0);
      cluster_arrive();
      mbar_wait(gfull, 1);
      mbar_wait(gfull + 8, 1);
      bar_sync(2 + wg, 256);
      wg_fence();
      HALF_STAGE(o, 7, 1);
      HALF_STAGE(o, 8, 3);
      wg_commit();
      STAMP(16);
      mbar_wait(gfull + 16, 1);
      STAMP(17);
      wg_fence();
      HALF_STAGE(o, 6, 11);
      wg_commit();
      bar_arrive(3 - wg, 256);
      mbar_wait(bar_par, 0);
      uint32_t* xo = g_xch + ((size_t)b * 8 * 256 + ct) * 4;
      const uint32_t* xi = g_xch + ((size_t)(b ^ 2) * 8 * 256 + ct) * 4;
      const uint32_t par1 = (~lds1(par + PAR_CONST + 4) & 1) << 16;
      uint32_t ga[16];
      uint4 bw[8];
#define LOAD_PAR _Pragma("unroll") for (int i = 0; i < 8; i++) {                                                               \
        ga[2 * i] = lds1(par + PAR_T2 + i * 128 + tq * 16 + 12); ga[2 * i + 1] = lds1(par + PAR_T2 + i * 128 + 64 + tq * 16 + 12); \
        bw[i] = lds4(par + PAR_T1 + i * 64 + tq * 16);                                                                          \
        if (!(g & 1)) { bw[i].x = 0x3f803f80u; bw[i].y = 0x3f803f80u; }                                                         \
      }
      if (PPOS == 0) LOAD_PAR
      wg_wait<1>();
      mbar_arrive_pred(bar_rel, lane0);
      wg_wait<0>();
      keep(o);
      mbar_arrive_pred(bar_ring, lane0);
      PROF(8, ct == PT, 20); STAMP(1);
#define SEND(i) st_b128(xo + (i) * 1024, (pack_bf(o[8 * (i)], o[8 * (i) + 1]) & ~0x10000u) | par1, pack_bf(o[8 * (i) + 2], o[8 * (i) + 3]), \
                        pack_bf(o[8 * (i) + 4], o[8 * (i) + 5]), pack_bf(o[8 * (i) + 6], o[8 * (i) + 7]))
#pragma unroll
      for (int i = 0; i < NS1; i++) SEND(i);
      PROF(8, ct == PT, 21); STAMP(2);
      bar_sync(2 + wg, 256);
      wg_fence();
      HALF_STAGE(s, 7, 0);
      HALF_STAGE(s, 8, 2);
      HALF_STAGE(s, 6, 10);
      wg_commit();
      bar_arrive(3 - wg, 256);
      STAMP(18);
      mbar_wait(gfull + 24, 1);
#pragma unroll
      for (int i = NS1; i < 8; i++) SEND(i);
      uint4 v[8];
#pragma unroll
      for (int i = 0; i < 4; i++) v[i] = ld_b128(xi + i * 1024);
      if (PPOS == 1) LOAD_PAR
      STAMP(19);
      mbar_wait(bar_xres, 0);
      wg_wait<0>();
      mbar_arrive_pred(bar_ring + 8, lane0);
      bar_sync(2 + wg, 256);
      STAMP(20);
#pragma unroll
      for (int i = 4; i < 8; i++) v[i] = ld_b128(xi + i * 1024);
      mbar_wait(bar_xres, 0);
      wg_fence();
      HALF_STAGE(s, 9, 4);
      wg_commit();
      mbar_wait(bar_rx, 0);
      wg_fence();
      HALF_STAGE(s, 1, 5);
      wg_commit();
      bar_arrive(3 - wg, 256);
      STAMP(21);
      wg_wait<0>();
      keep(s);
      mbar_arrive_pred(bar_ring + 16, lane0);
      PROF(10, ct == PT, 23); STAMP(4);
#pragma unroll
      for (int i = 0; i < 16; i += 2) ldmatrix4((trow ^ ((i & 7) << 4)) + (i >> 3) * 16384, xr[2 * i], xr[2 * i + 1], xr[2 * i + 2], xr[2 * i + 3]);
      if (PPOS == 2) LOAD_PAR
      uint32_t pk[32];
      pack_p(s, pk);
      keep(pk);
      {
        uint32_t n = 0;
        bool ok;
        do {
          ok = true;
#pragma unroll
          for (int i = 0; i < 8; i++)
            if ((v[i].x & 0x10000u) != par1) { v[i] = ld_b128(xi + i * 1024); ok = false; }
          watchdog(n);
        } while (!ok);
      }
      __syncwarp();
      PROF(8, ct == PT, 22); STAMP(3);
#pragma unroll
      for (int k = 0; k < 4; k++) sv[k] = ESV ? ld_b128(sp[k]) : make_uint4(0, 0, 0, 0);
      float ds[4] = {0.f, 0.f, 0.f, 0.f}, dl[4] = {0.f, 0.f, 0.f, 0.f}, q0[4] = {0.f, 0.f, 0.f, 0.f}, q1[4] = {0.f, 0.f, 0.f, 0.f};
#pragma unroll
      for (int i = 0; i < 8; i++) {
        const uint32_t u0 = hfma2(ga[2 * i], hadd2(pk[4 * i], v[i].x & ~0x10000u), xr[4 * i]);
        const uint32_t u1 = hfma2(ga[2 * i], hadd2(pk[4 * i + 1], v[i].y), xr[4 * i + 1]);
        const uint32_t u2 = hfma2(ga[2 * i + 1], hadd2(pk[4 * i + 2], v[i].z), xr[4 * i + 2]);
        const uint32_t u3 = hfma2(ga[2 * i + 1], hadd2(pk[4 * i + 3], v[i].w), xr[4 * i + 3]);
        xr[4 * i] = u0; xr[4 * i + 1] = u1; xr[4 * i + 2] = u2; xr[4 * i + 3] = u3;
        mma16816(ds, u0, u1, u2, u3, bw[i].x, bw[i].y);
        mma16816(dl, u0, u1, u2, u3, bw[i].z, bw[i].w);
        mma16816(q0, u0, u1, u2, u3, u0, u2);
        mma16816(q1, u0, u1, u2, u3, u1, u3);
      }
      const float sqa = __shfl_sync(0xffffffffu, (g & 1) ? q0[1] : q0[0], g * 4 + (g >> 1));
      const float sqb = __shfl_sync(0xffffffffu, (g & 1) ? q1[3] : q1[2], g * 4 + (g >> 1));
      own = (tq & 1) ? make_uint4(__float_as_uint(ds[2]), __float_as_uint(sqb), __float_as_uint(ds[3] + dl[3]), tag)
                                 : make_uint4(__float_as_uint(ds[0]), __float_as_uint(sqa), __float_as_uint(ds[1] + dl[1]), tag);
      if (tq < 2) st_b128(sp[0], own.x, own.y, own.z, own.w);
    }
    PROF(8, ct == PT, 29); STAMP(5);
    uint32_t mm, ih, il;
    float rbest;
    uint32_t wf[128];
    const uint32_t frow = (ln & 7) + (ln >> 4) * 8;
    const uint32_t wfo = base + (warp & 1) * 8192 + frow * 64 + ((((ln >> 3) & 1) ^ ((frow >> 1) & 3)) << 4);
#define LOAD_WF(m) _Pragma("unroll") for (int f = 0; f < 16; f++) {                                                   \
      const int r = ((f >> 1) * 4 + (m) * 2 + (f & 1)) * 4;                                                           \
      ldmatrix4t(((wfo + unit_of((m) ? FT_U : FT_G, warp >> 1)) ^ ((f & 1) * 32)) + (f >> 1) * 1024, wf[r], wf[r + 1], wf[r + 2], wf[r + 3]); \
    }
    bool early, wait1;
    {
#pragma unroll
      for (int i = 0; i < 16; i += 2) stmatrix4((trow ^ ((i & 7) << 4)) + (i >> 3) * 16384, xr[2 * i], xr[2 * i + 1], xr[2 * i + 2], xr[2 * i + 3]);
      const uint4 cst = lds4(par + PAR_CONST);
      const float A1 = __uint_as_float(cst.x), A2 = __uint_as_float(cst.z);
      uint32_t n = 0;
      early = false; wait1 = false;
#pragma unroll 1
      while (true) {
        uint32_t miss;
        asm volatile("{ .reg .pred p0, p1, p2, p3; .reg .b64 u, v; .reg .b128 w;\n"
                     "setp.ge.u32 p0, %22, 2; setp.ne.and.u32 p0, %4, %21, p0; setp.ne.u32 p1, %8, %21; setp.ne.u32 p2, %12, %21; setp.ne.u32 p3, %16, %21;\n"
                     "@p0 ld.relaxed.gpu.global.v4.u32 {%1, %2, %3, %4}, [%17];\n"
                     "@p1 ld.relaxed.gpu.global.v4.u32 {%5, %6, %7, %8}, [%18];\n"
                     "@p2 ld.relaxed.gpu.global.v4.u32 {%9, %10, %11, %12}, [%19];\n"
                     "@p3 ld.relaxed.gpu.global.v4.u32 {%13, %14, %15, %16}, [%20];\n"
                     "or.pred p0, p0, p1; or.pred p2, p2, p3; or.pred p0, p0, p2; vote.sync.any.pred p0, p0, 0xffffffff; selp.u32 %0, 1, 0, p0; }"
                     : "=r"(miss), "+r"(sv[0].x), "+r"(sv[0].y), "+r"(sv[0].z), "+r"(sv[0].w), "+r"(sv[1].x), "+r"(sv[1].y), "+r"(sv[1].z), "+r"(sv[1].w),
                       "+r"(sv[2].x), "+r"(sv[2].y), "+r"(sv[2].z), "+r"(sv[2].w), "+r"(sv[3].x), "+r"(sv[3].y), "+r"(sv[3].z), "+r"(sv[3].w)
                     : "l"(sp[0]), "l"(sp[1]), "l"(sp[2]), "l"(sp[3]), "r"(tag), "r"(tq) : "memory");
        if (!miss) break;
        wait1 = true;
        if (!early && (b >= NFFN || __all_sync(0xffffffffu, mbar_test(bar_box + (warp >> 1) * 8, 0)))) {
          early = true;
          LOAD_WF(0);
          __syncwarp();
          mbar_arrive_pred(bar_gate, lane0);
        }
        watchdog(n);
      }
      const uint4 v0 = tq < 2 ? own : sv[0], v1 = sv[1], v2 = sv[2], v3 = sv[3];
      PROF(8, ct == PT, 30); STAMP(6);
      float su = (__uint_as_float(v0.x) + __uint_as_float(v1.x)) + (__uint_as_float(v2.x) + __uint_as_float(v3.x));
      float sq = (__uint_as_float(v0.y) + __uint_as_float(v1.y)) + (__uint_as_float(v2.y) + __uint_as_float(v3.y));
      float dt = (__uint_as_float(v0.z) + __uint_as_float(v1.z)) + (__uint_as_float(v2.z) + __uint_as_float(v3.z));
      su += __shfl_xor_sync(0xffffffffu, su, 2); sq += __shfl_xor_sync(0xffffffffu, sq, 2); dt += __shfl_xor_sync(0xffffffffu, dt, 2);
      const float m = su * (1.f / DM);
      float mb, sd;
      ln_scalars(m, fmaxf(sq * (1.f / DM) - m * m, 0.f), mb, sd);
      const float inv = rcp(sd);
      rbest = (dt - mb * A1) * inv + A2;
      mm = pack_bf(mb, mb);
      ih = pack_bf(inv, inv);
      const float lo = inv - bf_lo(ih);
      il = pack_bf(lo, lo);
    }
    int ibest;
    {
      const uint32_t bits = __float_as_uint(rbest);
      const uint32_t key = (((int)bits < 0 ? ~bits : bits | 0x80000000u) & ~0x1ffu) | ((127 - lrow0 - (tq & 1) * 8) << 2) | tag;
      sts1(par + PAR_RED + warp * 4, __reduce_max_sync(0xffffffffu, key));
      PROF(8, ct == PT, 38); STAMP(7);
      uint32_t waited;
      asm volatile("{ .reg .pred p, q; setp.ne.u32 p, %1, 0; barrier.cta.red.or.pred q, 1, 256, p; selp.u32 %0, 1, 0, q; }" : "=r"(waited) : "r"((uint32_t)(wait1 && (wg || CW0))) : "memory");
      const uint4 ka = lds4(par + PAR_RED), kb = lds4(par + PAR_RED + 16);
      const uint32_t k2 = max(max(max(ka.x, ka.y), max(ka.z, ka.w)), max(max(kb.x, kb.y), max(kb.z, kb.w)));
      if (ct == 0 && ((cj & CWM) == 0 || (CWL && !waited))) st_relaxed(g_cand + rb, k2);
      ibest = 127 - ((k2 >> 2) & 127);
    }
    PROF(8, ct == PT, 39); STAMP(8);
    if ((ibest >> 4) == warp) {
      const int src = (ibest & 7) * 4 + ((ibest >> 3) & 1), ch = g * 2;
      const uint32_t cm = __shfl_sync(0xffffffffu, mm, src), ch_ = __shfl_sync(0xffffffffu, ih, src), cl = __shfl_sync(0xffffffffu, il, src);
      const uint32_t xa = res + (ch >> 3) * 16384 + ibest * 128 + (((ch & 7) ^ (ibest & 7)) << 4) + tq * 4;
      const uint32_t x0 = lds1(xa), x1 = lds1(xa ^ 16);
      const uint2 p0 = lds2(par + PAR_T2 + ch * 64 + tq * 16), p1 = lds2(par + PAR_T2 + ch * 64 + 64 + tq * 16);
      uint32_t* dst = g_row + rb * 2 * DM + cj * 128 + ln * 4;
      st_pairs(dst, ln_mod(x0, cm, ch_, cl, p0.x, p0.y), ln_mod(x1, cm, ch_, cl, p1.x, p1.y), tag);
      st_pairs(dst + DM, x0, x1, tag);
      __syncwarp();
    }
    PROF(8, ct == PT, 37); STAMP(9);
    uint32_t wd[64];
    const uint32_t wda = base + unit_of(FT_D, warp >> 1) + (warp & 1) * 8192 + frow * 128 + ((((ln >> 3) & 1) ^ (ln & 7)) << 4);
#define LOAD_WD(f) ldmatrix4t((wda ^ ((((f) >> 1) & 3) * 32)) + ((f) >> 3) * 4096 + ((f) & 1) * 2048, wd[4 * (f)], wd[4 * (f) + 1], wd[4 * (f) + 2], wd[4 * (f) + 3])
    if (!early) {
      if (b < NFFN) mbar_wait(bar_box + (warp >> 1) * 8, 0);
      LOAD_WF(0);
      __syncwarp();
      mbar_arrive_pred(bar_gate, lane0);
    }
    if (b < NFFN) {
      const uint32_t own = base + unit_of(FT_G, warp >> 1) + (warp & 1) * 8192;
      mbar_wait(bar_box + (4 + (warp >> 1)) * 8, 0);
      LOAD_WF(1);
      uint32_t* const ydst = g_ypart + ((size_t)(warp * 16 + tq * 2) * NFFN + b) * 8 + g;
      PROF(8, ct == PT, 31); STAMP(10);
      mbar_wait(bar_box + (8 + (warp >> 1)) * 8, 0);
#pragma unroll
      for (int f = 0; f < WDE; f++) LOAD_WD(f);
      STAMP(11);
      mbar_wait(bar_sel, 0);
      PROF(8, ct == PT, 33); STAMP(12);
      float d[8][4];
#pragma unroll
      for (int i = 0; i < 4; i++) { d[i][0] = 0.f; d[i][1] = 0.f; d[i][2] = 0.f; d[i][3] = 0.f; }
#pragma unroll
      for (int ks = 0; ks < 8; ks++) {
        const uint2 hb = lds2(own + 256 + ks * 32 + tq * 8);
#pragma unroll
        for (int mt = 0; mt < 4; mt++) {
          const int r = ks * 16 + mt * 4;
          mma16816(d[mt], wf[r], wf[r + 1], wf[r + 2], wf[r + 3], hb.x, hb.y);
        }
      }
      sts2(own + (tq * 8 + g) * 8, __float_as_uint((tq & 2) ? ((tq & 1) ? d[1][2] : d[1][0]) : ((tq & 1) ? d[0][2] : d[0][0])),
           __float_as_uint((tq & 2) ? ((tq & 1) ? d[3][2] : d[3][0]) : ((tq & 1) ? d[2][2] : d[2][0])));
      bar_sync(1, 256);
      uint32_t ab[4];
      {
        float G = 0.f, U = 0.f;
        uint2 pv[8];
#pragma unroll
        for (int w8 = 0; w8 < 8; w8++) pv[w8] = lds2(base + ln * 8 + ((FT_G >> (w8 >> 1) * 4) & 15) * UNIT + (w8 & 1) * 8192);
#pragma unroll
        for (int w8 = 0; w8 < 8; w8 += 2) {
          G += __uint_as_float(pv[w8].x) + __uint_as_float(pv[w8 + 1].x);
          U += __uint_as_float(pv[w8].y) + __uint_as_float(pv[w8 + 1].y);
        }
#pragma unroll
        for (int f = WDE; f < 16; f++) LOAD_WD(f);
        const float act = rbf(silu_f(rbf(G))) * rbf(U);
        const uint32_t pk = pack_bf(act, __shfl_down_sync(0xffffffffu, act, 1));
#pragma unroll
        for (int i = 0; i < 4; i++) ab[i] = __shfl_sync(0xffffffffu, pk, i * 8 + tq * 2);
      }
      PROF(8, ct == PT, 34); STAMP(13);
#pragma unroll
      for (int mt = 0; mt < 8; mt++) {
        d[mt][0] = 0.f; d[mt][1] = 0.f; d[mt][2] = 0.f; d[mt][3] = 0.f;
        mma16816(d[mt], wd[mt * 8], wd[mt * 8 + 1], wd[mt * 8 + 2], wd[mt * 8 + 3], ab[0], ab[1]);
        mma16816(d[mt], wd[mt * 8 + 4], wd[mt * 8 + 5], wd[mt * 8 + 6], wd[mt * 8 + 7], ab[2], ab[3]);
      }
#pragma unroll
      for (int i = 0; i < 4; i++) {
        const int m4 = (i >> 1) * 4, e = (i & 1) * 2;
        const float y = (tq & 2) ? ((tq & 1) ? d[m4 + 3][e] : d[m4 + 2][e]) : ((tq & 1) ? d[m4 + 1][e] : d[m4][e]);
        st_relaxed(ydst + (m4 * 2 + (i & 1)) * NFFN * 8, tagf(y, tag));
      }
      PROF(8, ct == PT, 35); STAMP(14);
    }
    mbar_wait(bar_sel, 0);
    mbar_arrive_pred(bar_win, ct == 0);
    const int iwin = lds1(par + PAR_CONST + 60) & 0x7ff;
    {
      const uint32_t mm0 = __shfl_sync(0xffffffffu, mm, ln & ~1), mm1 = __shfl_sync(0xffffffffu, mm, ln | 1);
      const uint32_t ih0 = __shfl_sync(0xffffffffu, ih, ln & ~1), ih1 = __shfl_sync(0xffffffffu, ih, ln | 1);
      const uint32_t il0 = __shfl_sync(0xffffffffu, il, ln & ~1), il1 = __shfl_sync(0xffffffffu, il, ln | 1);
      const bool mine = (iwin >> 4) == rb * 8 + warp;
#pragma unroll 1
      for (int hf = 0; hf < 2; hf++) {
        uint32_t x[16];
#pragma unroll
        for (int i = 0; i < 8; i += 2) ldmatrix4((trow ^ (i << 4)) + hf * 16384, x[2 * i], x[2 * i + 1], x[2 * i + 2], x[2 * i + 3]);
#pragma unroll
        for (int i = 0; i < 8; i++) {
          const uint4 pv = lds4(par + PAR_T2 + (hf * 8 + i) * 64 + tq * 16);
          x[2 * i] = hadd2(x[2 * i], hmul2(pv.z, ln_mod(x[2 * i], mm0, ih0, il0, pv.x, pv.y)));
          x[2 * i + 1] = hadd2(x[2 * i + 1], hmul2(pv.z, ln_mod(x[2 * i + 1], mm1, ih1, il1, pv.x, pv.y)));
        }
        if (mine) {
          uint32_t* dst = reinterpret_cast<uint32_t*>(P.out + (size_t)grow0 * DM + cj * 128 + hf * 64) + tq;
#pragma unroll
          for (int i = 0; i < 8; i++) {
            if (grow0 != iwin) dst[i * 4] = x[2 * i];
            if (grow0 + 8 != iwin) dst[i * 4 + 4 * DM] = x[2 * i + 1];
          }
        } else {
#pragma unroll
          for (int i = 0; i < 8; i += 2) stmatrix4((trow ^ (i << 4)) + hf * 16384, x[2 * i], x[2 * i + 1], x[2 * i + 2], x[2 * i + 3]);
          fence_async_smem();
          __syncwarp();
          if (elect_one()) {
            tma2d_store(&maps.out, res + hf * 16384 + warp * 2048, cj * 128 + hf * 64, rb * 128 + warp * 16);
            asm volatile("cp.async.bulk.commit_group;" ::: "memory");
          }
        }
      }
      asm volatile("cp.async.bulk.wait_group.read 0;" ::: "memory");
    }
    PROF(8, ct == PT, 11); STAMP(15);
    cluster_wait();
  }
}

typedef CUresult (*EncodeFn)(CUtensorMap*, CUtensorMapDataType, cuuint32_t, void*, const cuuint64_t*, const cuuint64_t*,
                             const cuuint32_t*, const cuuint32_t*, CUtensorMapInterleave, CUtensorMapSwizzle,
                             CUtensorMapL2promotion, CUtensorMapFloatOOBfill);

void map2d(EncodeFn enc, CUtensorMap* m, const void* p, uint64_t rows, uint64_t cols, uint32_t brows) {
  cuuint64_t dims[2] = {cols, rows}, strides[1] = {cols * 2};
  cuuint32_t box[2] = {64, brows}, es[2] = {1, 1};
  enc(m, CU_TENSOR_MAP_DATA_TYPE_BFLOAT16, 2, const_cast<void*>(p), dims, strides, box, es, CU_TENSOR_MAP_INTERLEAVE_NONE,
      CU_TENSOR_MAP_SWIZZLE_128B, CU_TENSOR_MAP_L2_PROMOTION_L2_256B, CU_TENSOR_MAP_FLOAT_OOB_FILL_NONE);
}
void map2d_narrow(EncodeFn enc, CUtensorMap* m, const void* p, uint64_t rows, uint64_t cols, uint32_t brows) {
  cuuint64_t dims[2] = {cols, rows}, strides[1] = {cols * 2};
  cuuint32_t box[2] = {32, brows}, es[2] = {1, 1};
  enc(m, CU_TENSOR_MAP_DATA_TYPE_BFLOAT16, 2, const_cast<void*>(p), dims, strides, box, es, CU_TENSOR_MAP_INTERLEAVE_NONE,
      CU_TENSOR_MAP_SWIZZLE_64B, CU_TENSOR_MAP_L2_PROMOTION_L2_64B, CU_TENSOR_MAP_FLOAT_OOB_FILL_NONE);
}
void map3d(EncodeFn enc, CUtensorMap* m, const void* p, uint64_t rows, uint64_t cols, uint32_t brows, uint32_t nch) {
  cuuint64_t dims[3] = {64, rows, cols / 64}, strides[2] = {cols * 2, 128};
  cuuint32_t box[3] = {64, brows, nch}, es[3] = {1, 1, 1};
  enc(m, CU_TENSOR_MAP_DATA_TYPE_BFLOAT16, 3, const_cast<void*>(p), dims, strides, box, es, CU_TENSOR_MAP_INTERLEAVE_NONE,
      CU_TENSOR_MAP_SWIZZLE_128B, CU_TENSOR_MAP_L2_PROMOTION_L2_256B, CU_TENSOR_MAP_FLOAT_OOB_FILL_NONE);
}

}

extern "C" void kernel_launch(void* const* d_in, const int* in_sizes, int n_in, void* d_out, int out_size) {
  (void)in_sizes; (void)n_in; (void)out_size;
  static EncodeFn enc = nullptr;
  if (!enc) {
    void* fn = nullptr;
    cudaDriverEntryPointQueryResult st;
    cudaGetDriverEntryPoint("cuTensorMapEncodeTiled", &fn, cudaEnableDefault, &st);
    enc = (EncodeFn)fn;
    cudaFuncSetAttribute(fused_kernel, cudaFuncAttributeMaxDynamicSharedMemorySize, SMEM_BYTES);
  }
  Maps maps;
  map2d(enc, &maps.x, d_in[0], SEQ, DM, 128);
  map2d(enc, &maps.out, d_out, SEQ, DM, 16);
  map3d(enc, &maps.wq, d_in[3], DM, NQ, 64, 2);
  map3d(enc, &maps.k, d_in[1], 4 * SK, 128, 128, 1);
  map3d(enc, &maps.v, d_in[2], 4 * SK, 128, 128, 1);
  map3d(enc, &maps.wo, d_in[4], NQ, DM, 64, 2);
  map2d_narrow(enc, &maps.wg, d_in[7], DM, FF, 256);
  map2d_narrow(enc, &maps.wu, d_in[8], DM, FF, 256);
  map3d(enc, &maps.wd, d_in[9], FF, DM, 32, 4);
  map2d_narrow(enc, &maps.wm, d_in[11], DM, NMOD, 256);
  Ptrs p;
  p.x = (const __nv_bfloat16*)d_in[0];
  p.w_r = (const __nv_bfloat16*)d_in[6];
  p.w_gate = (const __nv_bfloat16*)d_in[7];
  p.w_up = (const __nv_bfloat16*)d_in[8];
  p.w_down = (const __nv_bfloat16*)d_in[9];
  p.c = (const __nv_bfloat16*)d_in[10];
  p.w_mod = (const __nv_bfloat16*)d_in[11];
  p.out = (__nv_bfloat16*)d_out;
  fused_kernel<<<NMAIN + NHELP, 384, SMEM_BYTES>>>(maps, p);
}
```

```cpp
#include <cuda_runtime.h>
#include <cuda_bf16.h>
#include <cuda.h>
#include <stdint.h>
#include <type_traits>

#define HD 1
#define HDX 2
#define XF 4
#define XE 32
#define XR 0
#define NRS 6
#define FPACE 3
#define GOST 20
#define WB 3
#define WN 24
#define RES0 17
#define RES1 20
#define HU 32
#define NS1 6
#define PG0 0
#define PSL 0
#define CWM 7
#define WDE 16
#define CWL 1
#define CW0 0
#define ESV 1
#define PPOS 1
#define FB0 0
#define FB2 8
#define OPS 8192
#define OFL 0
#define ODS 8
#define VREL 7
#define E0 3

namespace {

constexpr int SEQ = 2048, DM = 1024, NQ = 4096, SK = 2048, WIN = 512, FF = 3584, NMOD = 6144;
constexpr int NMAIN = 128, NHELP = 4, NFFN = 112;
constexpr int NSLOT = 4, SLOT_BYTES = 32768, UNIT = 16384, GST_BYTES = 3 * UNIT;
constexpr uint32_t XT1 = 0xDCBA, XT2 = 0x9687;
constexpr uint32_t WT0 = 0xA741, WT1 = 0x7420, WT2 = 0x4A20;
constexpr uint32_t AT0 = WT1, AT1 = WT2;
constexpr uint32_t QT = 0xDC9696DC;
constexpr int OFF_STAGE = 12 * UNIT;
constexpr uint32_t FT_G = 0x07B3, FT_U = 0xA628, FT_D = 0x5149;
constexpr int OFF_RES = 12 * UNIT;
constexpr int OFF_PAR = 14 * UNIT;
constexpr int OFF_BAR = OFF_PAR + 2528;
constexpr int SMEM_BYTES = OFF_BAR + 544;
static_assert(SMEM_BYTES <= 232448, "smem");

constexpr int PAR_T1 = 0;
constexpr int PAR_T2 = 512;
constexpr int PAR_CONST = 1536;
constexpr int PAR_RED = 1600;
constexpr int PAR_SINK = 2176;

struct Maps {
  CUtensorMap x, wq, k, v, wo, wg, wu, wd, wm, out;
};
struct Ptrs {
  const __nv_bfloat16 *x, *w_r, *c, *w_mod, *w_gate, *w_up, *w_down;
  __nv_bfloat16* out;
};

__device__ __align__(1024) uint8_t g_act[16 * 80 * UNIT];
__device__ __align__(128) uint32_t g_mod[NMOD];
__device__ __align__(128) uint32_t g_modp[2 * 2 * DM];
__device__ __align__(128) uint32_t g_ln1[SEQ * 4];
__device__ __align__(128) uint32_t g_cnt_h[16 * 32];
__device__ __align__(128) uint32_t g_cnt_o[128 * 32];
__device__ __align__(128) uint32_t g_xch[NMAIN * 8 * 256 * 4];
__device__ __align__(128) uint32_t g_stats[8 * SEQ * 4];
__device__ __align__(128) uint32_t g_cand[32];
__device__ __align__(128) uint32_t g_row[16 * 2 * DM];
__device__ __align__(128) uint32_t g_ypart[NMAIN * NFFN * 8];
__device__ uint32_t g_epoch;

__device__ __forceinline__ uint32_t fresh_lane() { uint32_t l; asm volatile("mov.u32 %0, %%laneid;" : "=r"(l)); return l; }
__device__ __forceinline__ uint32_t frag_offset(int warp) {
  const uint32_t l = fresh_lane();
  return ((warp & 3) * 16 + (l & 15)) * 128 + (((l >> 4) ^ (l & 7)) << 4);
}
__device__ __forceinline__ bool elect_one() {
  uint32_t p;
  asm volatile("{ .reg .pred q; elect.sync _|q, 0xffffffff; selp.u32 %0, 1, 0, q; }" : "=r"(p));
  return p;
}
__device__ __forceinline__ uint32_t smem_u32(const void* p) { return (uint32_t)__cvta_generic_to_shared(p); }
__device__ __forceinline__ void mbar_init(uint32_t bar, uint32_t cnt) {
  asm volatile("mbarrier.init.shared::cta.b64 [%0], %1;" ::"r"(bar), "r"(cnt) : "memory");
}
__device__ __forceinline__ void mbar_expect_tx(uint32_t bar, uint32_t bytes) {
  asm volatile("mbarrier.arrive.expect_tx.shared::cta.b64 _, [%0], %1;" ::"r"(bar), "r"(bytes) : "memory");
}
__device__ __forceinline__ void mbar_arrive(uint32_t bar) {
  asm volatile("mbarrier.arrive.shared::cta.b64 _, [%0];" ::"r"(bar) : "memory");
}
__device__ __forceinline__ void mbar_arrive_pred(uint32_t bar, bool p) {
  asm volatile("{ .reg .pred p; setp.ne.b32 p, %1, 0; @p mbarrier.arrive.shared::cta.b64 _, [%0]; }" ::"r"(bar), "r"((int)p) : "memory");
}
__device__ __forceinline__ void mbar_arrive_cl(uint32_t bar, uint32_t off, bool p = true) {
  asm volatile("{ .reg .pred p, q; .reg .b32 a; setp.ne.b32 q, %2, 0; setp.ne.and.b32 p, %0, 0, q; add.u32 a, %0, %1; @p mbarrier.arrive.shared::cluster.b64 _, [a]; }"
               ::"r"(bar), "r"(off), "r"((int)p) : "memory");
}
__device__ __forceinline__ uint32_t mapa(uint32_t addr, uint32_t cta) {
  uint32_t r; asm("mapa.shared::cluster.u32 %0, %1, %2;" : "=r"(r) : "r"(addr), "r"(cta)); return r;
}
__device__ __forceinline__ void cluster_arrive() { asm volatile("barrier.cluster.arrive.relaxed.aligned;" ::: "memory"); }
__device__ __forceinline__ void cluster_wait() { asm volatile("barrier.cluster.wait.aligned;" ::: "memory"); }
__device__ __forceinline__ void watchdog(uint32_t& n) {
}
__device__ __forceinline__ void mbar_wait(uint32_t bar, uint32_t parity) {
  asm volatile("{\n.reg .pred p;\nWAIT_%=:\nmbarrier.try_wait.parity.shared::cta.b64 p, [%0], %1;\n@!p bra WAIT_%=;\n}" ::"r"(bar), "r"(parity) : "memory");
}
__device__ __forceinline__ bool mbar_test(uint32_t bar, uint32_t parity) {
  uint32_t ok;
  asm volatile("{\n.reg .pred p;\nmbarrier.test_wait.parity.shared::cta.b64 p, [%1], %2;\nselp.u32 %0, 1, 0, p;\n}" : "=r"(ok) : "r"(bar), "r"(parity) : "memory");
  return ok;
}
__device__ __forceinline__ uint64_t l2_stream() {
  uint64_t f; asm("createpolicy.fractional.L2::evict_first.b64 %0, 1.0;" : "=l"(f)); return f;
}
__device__ __forceinline__ void tma2d(uint32_t dst, const CUtensorMap* m, int c0, int c1, uint32_t bar) {
  asm volatile("cp.async.bulk.tensor.2d.shared::cluster.global.mbarrier::complete_tx::bytes.L2::cache_hint [%0], [%1, {%3, %4}], [%2], %5;"
               ::"r"(dst), "l"(m), "r"(bar), "r"(c0), "r"(c1), "l"(l2_stream()) : "memory");
}
__device__ __forceinline__ void bulk_load(uint32_t dst, const void* src, uint32_t bytes, uint32_t bar) {
  asm volatile("cp.async.bulk.shared::cluster.global.mbarrier::complete_tx::bytes [%0], [%1], %2, [%3];" ::"r"(dst), "l"(src), "r"(bytes), "r"(bar) : "memory");
}
__device__ __forceinline__ void bulk_load_stream(uint32_t dst, const void* src, uint32_t bytes, uint32_t bar) {
  asm volatile("cp.async.bulk.shared::cluster.global.mbarrier::complete_tx::bytes.L2::cache_hint [%0], [%1], %2, [%3], %4;"
               ::"r"(dst), "l"(src), "r"(bytes), "r"(bar), "l"(l2_stream()) : "memory");
}
__device__ __forceinline__ void tma2d_store(const CUtensorMap* m, uint32_t src, int c0, int c1) {
  asm volatile("cp.async.bulk.tensor.2d.global.shared::cta.bulk_group [%0, {%2, %3}], [%1];" ::"l"(m), "r"(src), "r"(c0), "r"(c1) : "memory");
}
__device__ __forceinline__ void bulk_store(void* dst, uint32_t src, uint32_t bytes) {
  asm volatile("cp.async.bulk.global.shared::cta.bulk_group [%0], [%1], %2;" ::"l"(dst), "r"(src), "r"(bytes) : "memory");
}
__device__ __forceinline__ uint32_t unit_of(uint32_t table, uint32_t i) { return ((table >> (i * 4)) & 15) * UNIT; }
__device__ __forceinline__ void tma3d(uint32_t dst, const CUtensorMap* m, int c0, int c1, int c2, uint32_t bar) {
  asm volatile("cp.async.bulk.tensor.3d.shared::cluster.global.mbarrier::complete_tx::bytes.L2::cache_hint [%0], [%1, {%3, %4, %5}], [%2], %6;"
               ::"r"(dst), "l"(m), "r"(bar), "r"(c0), "r"(c1), "r"(c2), "l"(l2_stream()) : "memory");
}
template <bool STREAM>
__device__ __forceinline__ void tma3d_mc(uint32_t dst, const CUtensorMap* m, int c0, int c1, int c2, uint32_t bar) {
  if (STREAM)
    asm volatile("cp.async.bulk.tensor.3d.shared::cluster.global.mbarrier::complete_tx::bytes.multicast::cluster.L2::cache_hint [%0], [%1, {%3, %4, %5}], [%2], %6, %7;"
                 ::"r"(dst), "l"(m), "r"(bar), "r"(c0), "r"(c1), "r"(c2), "h"((uint16_t)3), "l"(l2_stream()) : "memory");
  else
    asm volatile("cp.async.bulk.tensor.3d.shared::cluster.global.mbarrier::complete_tx::bytes.multicast::cluster [%0], [%1, {%3, %4, %5}], [%2], %6;"
                 ::"r"(dst), "l"(m), "r"(bar), "r"(c0), "r"(c1), "r"(c2), "h"((uint16_t)3) : "memory");
}
__device__ __forceinline__ void prefetch_map(const CUtensorMap* m) {
  asm volatile("prefetch.tensormap [%0];" ::"l"(m) : "memory");
}
__device__ __forceinline__ void fence_async() { asm volatile("fence.proxy.async.global;" ::: "memory"); }
__device__ __forceinline__ void fence_async_smem() { asm volatile("fence.proxy.async.shared::cta;" ::: "memory"); }
__device__ __forceinline__ void bar_sync(int id, int n) { asm volatile("bar.sync %0, %1;" ::"r"(id), "r"(n) : "memory"); }
__device__ __forceinline__ void bar_arrive(int id, int n) { asm volatile("bar.arrive %0, %1;" ::"r"(id), "r"(n) : "memory"); }
__device__ __forceinline__ void wg_fence() { asm volatile("wgmma.fence.sync.aligned;" ::: "memory"); }
__device__ __forceinline__ void wg_commit() { asm volatile("wgmma.commit_group.sync.aligned;" ::: "memory"); }
template <int N> __device__ __forceinline__ void wg_wait() { asm volatile("wgmma.wait_group.sync.aligned %0;" ::"n"(N) : "memory"); }
__device__ __forceinline__ uint64_t make_desc(uint32_t addr, uint32_t lbo, uint32_t sbo) {
  return (uint64_t)((addr & 0x3FFFF) >> 4) | ((uint64_t)(lbo >> 4) << 16) | ((uint64_t)(sbo >> 4) << 32) | (1ull << 62);
}
__device__ __forceinline__ uint32_t ld_relaxed(const uint32_t* p) {
  uint32_t v; asm volatile("ld.relaxed.gpu.global.u32 %0, [%1];" : "=r"(v) : "l"(p) : "memory"); return v;
}
__device__ __forceinline__ uint32_t ld_acquire(const uint32_t* p) {
  uint32_t v; asm volatile("ld.acquire.gpu.global.u32 %0, [%1];" : "=r"(v) : "l"(p) : "memory"); return v;
}
__device__ __forceinline__ uint4 ld_relaxed4(const uint32_t* p) {
  uint4 v; asm volatile("ld.relaxed.gpu.global.v4.u32 {%0,%1,%2,%3}, [%4];" : "=r"(v.x), "=r"(v.y), "=r"(v.z), "=r"(v.w) : "l"(p) : "memory"); return v;
}
__device__ __forceinline__ uint2 ld_relaxed2(const uint32_t* p) {
  uint2 v; asm volatile("ld.relaxed.gpu.global.v2.u32 {%0,%1}, [%2];" : "=r"(v.x), "=r"(v.y) : "l"(p) : "memory"); return v;
}
__device__ __forceinline__ void st_relaxed(uint32_t* p, uint32_t v) {
  asm volatile("st.relaxed.gpu.global.u32 [%0], %1;" ::"l"(p), "r"(v) : "memory");
}
__device__ __forceinline__ void st_relaxed2(uint32_t* p, uint32_t a, uint32_t b) {
  asm volatile("st.relaxed.gpu.global.v2.u32 [%0], {%1,%2};" ::"l"(p), "r"(a), "r"(b) : "memory");
}
__device__ __forceinline__ void st_relaxed4(uint32_t* p, uint32_t a, uint32_t b, uint32_t c, uint32_t d) {
  asm volatile("st.relaxed.gpu.global.v4.u32 [%0], {%1,%2,%3,%4};" ::"l"(p), "r"(a), "r"(b), "r"(c), "r"(d) : "memory");
}
__device__ __forceinline__ void st_b128(uint32_t* p, uint32_t a, uint32_t b, uint32_t c, uint32_t d) {
  asm volatile("{ .reg .b64 u, v; .reg .b128 w; mov.b64 u, {%1, %2}; mov.b64 v, {%3, %4}; mov.b128 w, {u, v}; st.relaxed.gpu.global.b128 [%0], w; }"
               ::"l"(p), "r"(a), "r"(b), "r"(c), "r"(d) : "memory");
}
__device__ __forceinline__ uint4 ld_b128(const uint32_t* p) {
  uint4 r;
  asm volatile("{ .reg .b64 u, v; .reg .b128 w; ld.relaxed.gpu.global.b128 w, [%4]; mov.b128 {u, v}, w; mov.b64 {%0, %1}, u; mov.b64 {%2, %3}, v; }"
               : "=r"(r.x), "=r"(r.y), "=r"(r.z), "=r"(r.w) : "l"(p) : "memory");
  return r;
}
__device__ __forceinline__ void st_pairs(uint32_t* p, uint32_t a, uint32_t b, uint32_t tag) {
  asm volatile("{ .reg .b64 u, v; mov.b64 u, {%1, %3}; mov.b64 v, {%2, %3}; st.relaxed.gpu.global.v2.b64 [%0], {u, v}; }"
               ::"l"(p), "r"(a), "r"(b), "r"(tag) : "memory");
}
__device__ __forceinline__ uint4 ld_pairs(const uint32_t* p) {
  uint4 v;
  asm volatile("{ .reg .b64 u, v; ld.relaxed.gpu.global.v2.b64 {u, v}, [%4]; mov.b64 {%0, %1}, u; mov.b64 {%2, %3}, v; }"
               : "=r"(v.x), "=r"(v.y), "=r"(v.z), "=r"(v.w) : "l"(p) : "memory");
  return v;
}
__device__ __forceinline__ uint2 ld_pair(const uint32_t* p) {
  uint2 v;
  asm volatile("{ .reg .b64 u; ld.relaxed.gpu.global.b64 u, [%2]; mov.b64 {%0, %1}, u; }" : "=r"(v.x), "=r"(v.y) : "l"(p) : "memory");
  return v;
}
__device__ __forceinline__ void red_release(uint32_t* p, uint32_t v) {
  asm volatile("red.release.gpu.global.add.u32 [%0], %1;" ::"l"(p), "r"(v) : "memory");
}
__device__ __forceinline__ uint32_t ldg_nc1(const void* p) {
  uint32_t v;
  asm volatile("ld.global.nc.u32 %0, [%1];" : "=r"(v) : "l"(p));
  return v;
}
__device__ __forceinline__ uint4 ldg_nc4(const void* p) {
  uint4 v; asm volatile("ld.global.nc.L1::no_allocate.v4.u32 {%0,%1,%2,%3}, [%4];" : "=r"(v.x), "=r"(v.y), "=r"(v.z), "=r"(v.w) : "l"(p)); return v;
}
__device__ __forceinline__ uint4 ldg_stream4(const void* p) {
  uint4 v;
  asm volatile("ld.global.nc.L1::no_allocate.L2::cache_hint.v4.u32 {%0,%1,%2,%3}, [%4], %5;" : "=r"(v.x), "=r"(v.y), "=r"(v.z), "=r"(v.w) : "l"(p), "l"(l2_stream()));
  return v;
}
__device__ __forceinline__ void stg4(void* p, uint4 v) {
  asm volatile("st.global.v4.u32 [%0], {%1,%2,%3,%4};" ::"l"(p), "r"(v.x), "r"(v.y), "r"(v.z), "r"(v.w) : "memory");
}
__device__ __forceinline__ void wait_counter(const uint32_t* p, uint32_t target) {
  uint32_t n = 0;
  while ((int)(ld_acquire(p) - target) < 0) { watchdog(n); }
}
__device__ __forceinline__ uint32_t tagf(float v, uint32_t tag) { return (__float_as_uint(v) & ~3u) | tag; }
__device__ __forceinline__ bool tag_ok(uint4 v, uint32_t tag) { return (((v.x ^ tag) | (v.y ^ tag) | (v.z ^ tag) | (v.w ^ tag)) & 3u) == 0; }
__device__ __forceinline__ float untag_sum(uint32_t a, uint32_t b) { return __uint_as_float(a & ~3u) + __uint_as_float(b & ~3u); }
__device__ __forceinline__ uint4 poll4(const uint32_t* p, uint32_t tag) {
  uint4 v = ld_relaxed4(p);
  uint32_t n = 0;
  while (!tag_ok(v, tag)) { v = ld_relaxed4(p); watchdog(n); }
  return v;
}
__device__ __forceinline__ float bf_lo(uint32_t v) { return __uint_as_float(v << 16); }
__device__ __forceinline__ float bf_hi(uint32_t v) { return __uint_as_float(v & 0xffff0000u); }
__device__ __forceinline__ uint32_t pack_bf(float lo, float hi) {
  uint32_t r; asm("cvt.rn.bf16x2.f32 %0, %1, %2;" : "=r"(r) : "f"(hi), "f"(lo)); return r;
}
__device__ __forceinline__ float rbf(float v) { return __uint_as_float(pack_bf(0.f, v) & 0xffff0000u); }
__device__ __forceinline__ uint32_t hmul2(uint32_t a, uint32_t b) {
  uint32_t r; asm("mul.rn.bf16x2 %0, %1, %2;" : "=r"(r) : "r"(a), "r"(b)); return r;
}
__device__ __forceinline__ uint32_t hadd2(uint32_t a, uint32_t b) {
  uint32_t r; asm("add.rn.bf16x2 %0, %1, %2;" : "=r"(r) : "r"(a), "r"(b)); return r;
}
__device__ __forceinline__ uint32_t hsub2(uint32_t a, uint32_t b) {
  uint32_t r; asm("sub.rn.bf16x2 %0, %1, %2;" : "=r"(r) : "r"(a), "r"(b)); return r;
}
__device__ __forceinline__ uint32_t hmax2(uint32_t a, uint32_t b) {
  uint32_t r; asm("max.bf16x2 %0, %1, %2;" : "=r"(r) : "r"(a), "r"(b)); return r;
}
__device__ __forceinline__ float rcp(float x) { float r; asm("rcp.approx.ftz.f32 %0, %1;" : "=f"(r) : "f"(x)); return r; }
__device__ __forceinline__ float ex2(float x) { float r; asm("ex2.approx.ftz.f32 %0, %1;" : "=f"(r) : "f"(x)); return r; }
__device__ __forceinline__ void stmatrix4(uint32_t addr, uint32_t a, uint32_t b, uint32_t c, uint32_t d) {
  asm volatile("stmatrix.sync.aligned.m8n8.x4.shared.b16 [%0], {%1,%2,%3,%4};" ::"r"(addr), "r"(a), "r"(b), "r"(c), "r"(d) : "memory");
}
__device__ __forceinline__ void ldmatrix4(uint32_t addr, uint32_t& a, uint32_t& b, uint32_t& c, uint32_t& d) {
  asm volatile("ldmatrix.sync.aligned.m8n8.x4.shared.b16 {%0,%1,%2,%3}, [%4];" : "=r"(a), "=r"(b), "=r"(c), "=r"(d) : "r"(addr) : "memory");
}
__device__ __forceinline__ void ldmatrix4t(uint32_t addr, uint32_t& a, uint32_t& b, uint32_t& c, uint32_t& d) {
  asm volatile("ldmatrix.sync.aligned.m8n8.x4.trans.shared.b16 {%0,%1,%2,%3}, [%4];" : "=r"(a), "=r"(b), "=r"(c), "=r"(d) : "r"(addr) : "memory");
}
__device__ __forceinline__ void mma16816(float (&d)[4], uint32_t a0, uint32_t a1, uint32_t a2, uint32_t a3, uint32_t b0, uint32_t b1) {
  asm volatile("mma.sync.aligned.m16n8k16.row.col.f32.bf16.bf16.f32 {%0,%1,%2,%3}, {%4,%5,%6,%7}, {%8,%9}, {%0,%1,%2,%3};"
               : "+f"(d[0]), "+f"(d[1]), "+f"(d[2]), "+f"(d[3]) : "r"(a0), "r"(a1), "r"(a2), "r"(a3), "r"(b0), "r"(b1));
}
__device__ __forceinline__ void sts1(uint32_t a, uint32_t v) { asm volatile("st.shared.u32 [%0], %1;" ::"r"(a), "r"(v) : "memory"); }
__device__ __forceinline__ uint4 lds4(uint32_t a) {
  uint4 v; asm volatile("ld.shared.v4.u32 {%0,%1,%2,%3}, [%4];" : "=r"(v.x), "=r"(v.y), "=r"(v.z), "=r"(v.w) : "r"(a) : "memory"); return v;
}
__device__ __forceinline__ uint2 lds2(uint32_t a) {
  uint2 v; asm volatile("ld.shared.v2.u32 {%0,%1}, [%2];" : "=r"(v.x), "=r"(v.y) : "r"(a) : "memory"); return v;
}
__device__ __forceinline__ uint32_t lds1(uint32_t a) {
  uint32_t v; asm volatile("ld.shared.u32 %0, [%1];" : "=r"(v) : "r"(a) : "memory"); return v;
}
__device__ __forceinline__ void sts2(uint32_t a, uint32_t x, uint32_t y) { asm volatile("st.shared.v2.u32 [%0], {%1,%2};" ::"r"(a), "r"(x), "r"(y) : "memory"); }
__device__ __forceinline__ void sts4(uint32_t a, uint4 v) {
  asm volatile("st.shared.v4.u32 [%0], {%1,%2,%3,%4};" ::"r"(a), "r"(v.x), "r"(v.y), "r"(v.z), "r"(v.w) : "memory");
}
__device__ __forceinline__ float silu_f(float v) { return __fdividef(v, 1.f + __expf(-v)); }
__device__ __forceinline__ uint32_t hfma2(uint32_t a, uint32_t b, uint32_t c) {
  uint32_t r; asm("fma.rn.bf16x2 %0, %1, %2, %3;" : "=r"(r) : "r"(a), "r"(b), "r"(c)); return r;
}
__device__ __forceinline__ void split_inv(float sd, uint32_t& ih, uint32_t& il) {
  const float inv = rcp(sd);
  ih = pack_bf(inv, inv);
  const float lo = inv - bf_lo(ih);
  il = pack_bf(lo, lo);
}
__device__ __forceinline__ uint32_t ln_mod(uint32_t x, uint32_t mean2, uint32_t ih, uint32_t il, uint32_t c1, uint32_t sh) {
  const uint32_t d = hsub2(x, mean2);
  return hadd2(hmul2(hfma2(d, ih, hmul2(d, il)), c1), sh);
}

#define R8(a, i) "+f"(a[i]), "+f"(a[i + 1]), "+f"(a[i + 2]), "+f"(a[i + 3]), "+f"(a[i + 4]), "+f"(a[i + 5]), "+f"(a[i + 6]), "+f"(a[i + 7])
#define D64 "{%0,%1,%2,%3,%4,%5,%6,%7,%8,%9,%10,%11,%12,%13,%14,%15,%16,%17,%18,%19,%20,%21,%22,%23,%24,%25,%26,%27,%28,%29,%30,%31," \
            "%32,%33,%34,%35,%36,%37,%38,%39,%40,%41,%42,%43,%44,%45,%46,%47,%48,%49,%50,%51,%52,%53,%54,%55,%56,%57,%58,%59,%60,%61,%62,%63}"
template <int TB>
__device__ __forceinline__ void mma_ss(float (&d)[64], uint64_t da, uint64_t db, int sc) {
  asm volatile("{\n.reg .pred p;\nsetp.ne.b32 p, %66, 0;\n"
               "wgmma.mma_async.sync.aligned.m64n128k16.f32.bf16.bf16 " D64 ", %64, %65, p, 1, 1, 0, %67;\n}"
               : R8(d, 0), R8(d, 8), R8(d, 16), R8(d, 24), R8(d, 32), R8(d, 40), R8(d, 48), R8(d, 56)
               : "l"(da), "l"(db), "r"(sc), "n"(TB));
}
template <int TB>
__device__ __forceinline__ void mma_rs(float (&d)[64], uint32_t a0, uint32_t a1, uint32_t a2, uint32_t a3, uint64_t db, int sc) {
  asm volatile("{\n.reg .pred p;\nsetp.ne.b32 p, %69, 0;\n"
               "wgmma.mma_async.sync.aligned.m64n128k16.f32.bf16.bf16 " D64 ", {%64,%65,%66,%67}, %68, p, 1, 1, %70;\n}"
               : R8(d, 0), R8(d, 8), R8(d, 16), R8(d, 24), R8(d, 32), R8(d, 40), R8(d, 48), R8(d, 56)
               : "r"(a0), "r"(a1), "r"(a2), "r"(a3), "l"(db), "r"(sc), "n"(TB));
}
#define D128 "{%0,%1,%2,%3,%4,%5,%6,%7,%8,%9,%10,%11,%12,%13,%14,%15,%16,%17,%18,%19,%20,%21,%22,%23,%24,%25,%26,%27,%28,%29,%30,%31," \
             "%32,%33,%34,%35,%36,%37,%38,%39,%40,%41,%42,%43,%44,%45,%46,%47,%48,%49,%50,%51,%52,%53,%54,%55,%56,%57,%58,%59,%60,%61,%62,%63," \
             "%64,%65,%66,%67,%68,%69,%70,%71,%72,%73,%74,%75,%76,%77,%78,%79,%80,%81,%82,%83,%84,%85,%86,%87,%88,%89,%90,%91,%92,%93,%94,%95," \
             "%96,%97,%98,%99,%100,%101,%102,%103,%104,%105,%106,%107,%108,%109,%110,%111,%112,%113,%114,%115,%116,%117,%118,%119,%120,%121,%122,%123,%124,%125,%126,%127}"
#define R128(d, e) R8(d, 0), R8(d, 8), R8(d, 16), R8(d, 24), R8(d, 32), R8(d, 40), R8(d, 48), R8(d, 56), \
                   R8(e, 0), R8(e, 8), R8(e, 16), R8(e, 24), R8(e, 32), R8(e, 40), R8(e, 48), R8(e, 56)
__device__ __forceinline__ void mma256_ss(float (&d)[64], float (&e)[64], uint64_t da, uint64_t db, int sc) {
  asm volatile("{\n.reg .pred p;\nsetp.ne.b32 p, %130, 0;\n"
               "wgmma.mma_async.sync.aligned.m64n256k16.f32.bf16.bf16 " D128 ", %128, %129, p, 1, 1, 0, 1;\n}"
               : R128(d, e) : "l"(da), "l"(db), "r"(sc));
}
__device__ __forceinline__ void mma256_rs(float (&d)[64], float (&e)[64], uint32_t a0, uint32_t a1, uint32_t a2, uint32_t a3, uint64_t db) {
  asm volatile("{\n.reg .pred p;\nsetp.ne.b32 p, 1, 0;\n"
               "wgmma.mma_async.sync.aligned.m64n256k16.f32.bf16.bf16 " D128 ", {%128,%129,%130,%131}, %132, p, 1, 1, 1;\n}"
               : R128(d, e) : "r"(a0), "r"(a1), "r"(a2), "r"(a3), "l"(db));
}
template <int N> __device__ __forceinline__ void keep(float (&a)[N]) {
#pragma unroll
  for (int i = 0; i < N; i++) asm volatile("" : "+f"(a[i])::"memory");
}
template <int N> __device__ __forceinline__ void keep(uint32_t (&a)[N]) {
#pragma unroll
  for (int i = 0; i < N; i++) asm volatile("" : "+r"(a[i])::"memory");
}

#define STAMP(idx) do {} while (0)
#define PROF(grp, cond, idx) do {} while (0)

constexpr float SCL2 = 1.4426950408889634f * 0.08838834764831845f;

__device__ __forceinline__ void pack_p(const float (&s)[64], uint32_t (&p)[32]) {
#pragma unroll
  for (int i = 0; i < 32; i++) p[i] = pack_bf(s[2 * i], s[2 * i + 1]);
}

__device__ __forceinline__ void issue_qk(float (&s)[64], uint32_t q0, uint32_t q1, uint32_t kslot) {
  const uint64_t db = make_desc(kslot, 16, 1024), da0 = make_desc(q0, 16, 1024), da1 = make_desc(q1, 16, 1024);
#pragma unroll
  for (int kk = 0; kk < 8; kk++) mma_ss<0>(s, (kk < 4 ? da0 : da1) + (kk & 3) * 2, db + (kk >> 2) * 1024 + (kk & 3) * 2, kk != 0);
}
__device__ __forceinline__ void issue_pv(float (&o)[64], uint32_t (&p)[32], uint32_t vslot, int acc) {
  uint64_t db = make_desc(vslot, 16384, 1024);
#pragma unroll
  for (int kk = 0; kk < 8; kk++)
    mma_rs<1>(o, p[4 * kk], p[4 * kk + 1], p[4 * kk + 2], p[4 * kk + 3], db + kk * 128, kk == 0 ? acc : 1);
}

template <int H>
__device__ __forceinline__ void store_chunk(const float (&a)[64], uint32_t addr) {
#pragma unroll
  for (int i = 8 * H; i < 8 * H + 8; i += 2)
    stmatrix4(addr ^ ((i & 7) << 4), pack_bf(a[4 * i], a[4 * i + 1]), pack_bf(a[4 * i + 2], a[4 * i + 3]),
              pack_bf(a[4 * i + 4], a[4 * i + 5]), pack_bf(a[4 * i + 6], a[4 * i + 7]));
}
template <int H>
__device__ __forceinline__ void store_chunk(const float (&a)[64], float i0, float i1, uint32_t addr) {
#pragma unroll
  for (int i = 8 * H; i < 8 * H + 8; i += 2)
    stmatrix4(addr ^ ((i & 7) << 4), pack_bf(a[4 * i] * i0, a[4 * i + 1] * i0), pack_bf(a[4 * i + 2] * i1, a[4 * i + 3] * i1),
              pack_bf(a[4 * i + 4] * i0, a[4 * i + 5] * i0), pack_bf(a[4 * i + 6] * i1, a[4 * i + 7] * i1));
}
__device__ __forceinline__ float inv_quad_sum(float l) {
  l += __shfl_xor_sync(0xffffffffu, l, 1);
  l += __shfl_xor_sync(0xffffffffu, l, 2);
  return rcp(l);
}

__device__ __forceinline__ void ln_scalars(float mean, float var, float& mb, float& sd) {
  mb = rbf(mean);
  float r; asm("sqrt.approx.ftz.f32 %0, %1;" : "=f"(r) : "f"(rbf(rbf(var) + 1e-5f)));
  sd = rbf(r);
}

__global__ void __cluster_dims__(2, 1, 1) __launch_bounds__(384, 1) fused_kernel(const __grid_constant__ Maps maps, const Ptrs P) {
  extern __shared__ __align__(1024) uint8_t smem_raw[];
  const uint32_t base = smem_u32(smem_raw);
  const int tid = threadIdx.x, lane = tid & 31;
  const int warp = __shfl_sync(0xffffffffu, tid >> 5, 0);
  const int b = blockIdx.x;
  PROF(31, tid == 0, 0);

  if (b >= NMAIN) {
    float* sc = reinterpret_cast<float*>(smem_raw);
    float* red = sc + DM;
    for (int k = tid; k < DM; k += 384) sc[k] = rbf(silu_f(__bfloat162float(P.c[k])));
    __syncthreads();
    if (tid < 256) {
      const int col = 2048 + (b - NMAIN) * 1024 + (tid & 127) * 8, r0 = (tid >> 7) * 512;
      float acc[8];
#pragma unroll
      for (int e = 0; e < 8; e++) acc[e] = 0.f;
#pragma unroll 1
      for (int r = r0; r < r0 + 512; r += HU) {
        uint4 w[HU];
#pragma unroll
        for (int u = 0; u < HU; u++) w[u] = ldg_stream4(P.w_mod + (size_t)(r + u) * NMOD + col);
#pragma unroll
        for (int u = 0; u < HU; u++) {
          float s = sc[r + u];
          acc[0] += s * bf_lo(w[u].x); acc[1] += s * bf_hi(w[u].x); acc[2] += s * bf_lo(w[u].y); acc[3] += s * bf_hi(w[u].y);
          acc[4] += s * bf_lo(w[u].z); acc[5] += s * bf_hi(w[u].z); acc[6] += s * bf_lo(w[u].w); acc[7] += s * bf_hi(w[u].w);
        }
      }
      if (tid >= 128) {
#pragma unroll
        for (int e = 0; e < 8; e++) red[(tid & 127) * 8 + e] = acc[e];
      }
      const uint32_t tag = ld_relaxed(&g_epoch) % 3 + 1;
      bar_sync(1, 256);
      if (tid < 128) {
        uint32_t o[8];
#pragma unroll
        for (int e = 0; e < 8; e++) o[e] = __float_as_uint(rbf(acc[e] + red[tid * 8 + e])) | tag;
        st_relaxed4(g_mod + col, o[0], o[1], o[2], o[3]);
        st_relaxed4(g_mod + col + 4, o[4], o[5], o[6], o[7]);
        const uint4 wr = ldg_nc4(P.w_r + tid * 8);
        const uint32_t wv[4] = {wr.x, wr.y, wr.z, wr.w};
        float dsum = 0.f;
#pragma unroll
        for (int e = 0; e < 8; e++) {
          const float m = bf_hi(o[e]);
          dsum += (b == NMAIN + 2 ? rbf(1.f + m) : m) * ((e & 1) ? bf_hi(wv[e >> 1]) : bf_lo(wv[e >> 1]));
        }
#pragma unroll
        for (int k = 16; k > 0; k >>= 1) dsum += __shfl_xor_sync(0xffffffffu, dsum, k);
        if (lane == 0) st_relaxed(g_mod + (b - NMAIN) * 4 + warp, tagf(dsum, tag));
      }
    }
    PROF(2, tid == 0, 1);
    return;
  }

  const int rank = b & 1;
  const int rb = ((b >> 4) << 1) | rank, cj = (b >> 1) & 7;
  const uint32_t bfull = base + OFF_BAR, bempty = bfull + NSLOT * 8;
  const uint32_t gfull = bempty + NSLOT * 8, gempty = gfull + 32;
  const uint32_t bar_ofull = gempty + 32;
  const uint32_t bar_ofree = bar_ofull + 32;
  const uint32_t bar_par = bar_ofree + 32;
  const uint32_t bar_mod = bar_par + 8;
  const uint32_t bar_pread = bar_mod + 8;
  const uint32_t bar_xres = bar_pread + 8;
  const uint32_t bar_ring = bar_xres + 8;
  const uint32_t bar_box = bar_ring + 24;
  const uint32_t bar_go = bar_box + 96;
  const uint32_t bar_go2 = bar_go + 16;
  const uint32_t bar_cnt = bar_go + 24;
  const uint32_t xfull = bar_go + 32, xempty = xfull + 32;
  const uint32_t bar_hw = xempty + 32, bar_hx = bar_hw + 8;
  const uint32_t bar_hpub = bar_hx + 16;
  const uint32_t bar_win = bar_hpub + 8;
  const uint32_t bar_rx = bar_win + 8;
  const uint32_t bar_sel = bar_rx + 8;
  const uint32_t bar_gate = bar_sel + 8;
  const uint32_t bar_rel = bar_gate + 8;
  const uint32_t bar_od = bar_rel + 8;
  const uint32_t bar_res = bar_go + 8;
  const uint32_t stage = base + OFF_STAGE, par = base + OFF_PAR;

  if (warp == 8 && elect_one()) {
    for (int s = 0; s < NSLOT; s++) { mbar_init(bfull + s * 8, 1); mbar_init(bempty + s * 8, 16); }
    for (int s = 0; s < 4; s++) { mbar_init(gfull + s * 8, 1); mbar_init(gempty + s * 8, 16); mbar_init(xfull + s * 8, 1); mbar_init(xempty + s * 8, 8); mbar_init(bar_ofree + s * 8, 1); mbar_init(bar_ofull + s * 8, 128); }
    mbar_init(bar_par, 64); mbar_init(bar_mod, 256); mbar_init(bar_pread, 8); mbar_init(bar_xres, 1);
    mbar_init(bar_ring, 8); mbar_init(bar_ring + 8, 8); mbar_init(bar_ring + 16, 8);
    mbar_init(bar_go, 1); mbar_init(bar_go2, 1); mbar_init(bar_cnt, 1); mbar_init(bar_hpub, 8); mbar_init(bar_res, 1); mbar_init(bar_win, 1); mbar_init(bar_rx, 1); mbar_init(bar_sel, 64); mbar_init(bar_gate, 8); mbar_init(bar_rel, 8); mbar_init(bar_od, 1);
    for (int s = 0; s < 12; s++) mbar_init(bar_box + s * 8, 1);
    asm volatile("fence.mbarrier_init.release.cluster;" ::: "memory");
    prefetch_map(&maps.x); prefetch_map(&maps.wq); prefetch_map(&maps.k); prefetch_map(&maps.v);
  }
  if (warp == 9 && elect_one()) {
    mbar_init(bar_hw, 1); mbar_init(bar_hx, 1); mbar_init(bar_hx + 8, 1);
    asm volatile("fence.mbarrier_init.release.cluster;" ::: "memory");
    mbar_expect_tx(bar_hw, 32768);
    mbar_expect_tx(bar_hx, 16384);
    mbar_expect_tx(bar_hx + 8, 16384);
    const __nv_bfloat16* xs = P.x + (size_t)(rb * 128 + cj * 16) * DM;
    bulk_load(base + 2 * GST_BYTES, xs, 16384, bar_hx);
    tma2d(stage, &maps.wm, (b >> 1) * 32, rank * 512, bar_hw);
    tma2d(stage + 16384, &maps.wm, (b >> 1) * 32, rank * 512 + 256, bar_hw);
    bulk_load(base + 3 * GST_BYTES, xs + 8 * DM, 16384, bar_hx + 8);
  }
  cluster_arrive();

  if (warp >= 8) {
    asm volatile("setmaxnreg.dec.sync.aligned.u32 40;");
    if (warp < 10) bar_arrive(1, 320);
    const uint32_t epoch = ld_relaxed(&g_epoch);
    cluster_wait();
    if (warp == 8) {
      const int kvrow = (cj >> 1) * SK + (SK - WIN);
      int wch = cj * 8 + rank * 2;
#pragma unroll 1
      for (int ps = 0; ps < 3; ps++) {
        const CUtensorMap* mw = ps == 2 ? &maps.wo : &maps.wq;
        const uint32_t xt = ps == 1 ? XT1 : XT2, wt = ps == 0 ? WT0 : (ps == 1 ? WT1 : WT2);
        const int nst = ps == 2 ? 32 : 16;
#pragma unroll 1
        for (int i = 0; i < nst; i++) {
          const uint32_t bf = gfull + (i & 3) * 8;
          const int kt = ps == 2 ? (((cj & 1) * 4 + ((i >> 1) & 3)) * 4 + (i >> 3)) * 2 + (i & 1) : (i + (ps ? 0 : b & 14)) & 15;
          const uint32_t wd = base + unit_of(wt, i & 3) + rank * UNIT, xd = base + unit_of(xt, i & 3);
          const uint8_t* xs = g_act + (uint32_t)(rb * 80 + (ps - 1) * 16 + kt) * UNIT;
          if (ps == 0 && i == HD) mbar_wait(bar_mod, 0);
          const bool xfirst = ps && i < 2;
          if (ps == 2 && i == 0) mbar_wait(bar_ofree + 24, 0);
          if (i == 0) fence_async();
          mbar_wait(gempty + (i & 3) * 8, ((i >> 2) & 1) ^ 1);
          if (elect_one()) {
            mbar_expect_tx(bf, ps ? GST_BYTES : 2 * UNIT);
            if (xfirst) bulk_load_stream(xd, xs, UNIT, bf);
          }
          if (ps && i < 4) mbar_wait(bempty + i * 8, 1);
          if (elect_one()) tma3d_mc<true>(wd, mw, 0, (i == 31 ? kt ^ (rank * 32) : kt) * 64, i == 31 ? cj * 2 : wch, bf);
          if (ps) {
            if (i == 16) { mbar_wait(bar_cnt, 0); fence_async(); }
            if (i == 2) mbar_wait(bar_ofree + (ps - 1) * 16, 0);
            if (elect_one()) {
              if (i == 31) bulk_load(xd, xs, UNIT, bf); else if (!xfirst) bulk_load_stream(xd, xs, UNIT, bf);
              mbar_arrive_pred(bar_go, i == GOST - 1);
              mbar_arrive_pred(bar_od, i == ODS);
              mbar_arrive_pred(bar_res, ((1u << RES0 | 1u << RES1) >> i) & 1);
            }
          }
        }
        if (ps == 2) break;
        wch = ps ? ((wch >> 3) ^ rank) * 2 : wch + 4;
#pragma unroll 1
        for (int u = 0; u < 16; u++) {
          const bool isk = (u == 0) || ((u & 1) && u < 15);
          const int blk = (isk ? (u + 1) >> 1 : (u == 15 ? 7 : (u >> 1) - 1)) & 3;
          const uint32_t sl = base + unit_of(ps ? AT1 : AT0, u & 3) + rank * UNIT, bf = bfull + (u & 3) * 8;
          if (u < 4) mbar_wait(gempty + ((u + 1) >> 1) * 8, 1);
          mbar_wait(bempty + (u & 3) * 8, ((u >> 2) & 1) ^ 1);
          if (elect_one()) {
            mbar_arrive_pred(bar_go2, ps && u == PG0);
            mbar_expect_tx(bf, SLOT_BYTES);
            tma3d_mc<false>(sl, isk ? &maps.k : &maps.v, 0, kvrow + blk * 128, rank, bf);
          }
        }
      }
      if (elect_one()) mbar_expect_tx(bar_rx, UNIT);
      mbar_wait(bar_rel, 0);
      if (elect_one()) {
        bulk_load_stream(base + UNIT, g_act + (uint32_t)(rb * 80 + 16 + 63 - (cj & 1) * 32) * UNIT, UNIT, bar_rx);
      }
      if (b < NFFN) {
#pragma unroll 1
        for (int u = 0; u < 12; u++) {
          const uint32_t dst = base + unit_of(u < 4 ? FT_G : (u < 8 ? FT_U : FT_D), u & 3);
          if (elect_one()) mbar_expect_tx(bar_box + u * 8, UNIT);
          if (u == FB0 || u == 2 || u == FB2) mbar_wait(bar_ring + (u == FB2 ? 16 : (u + 6) & 8), 0);
          if (u >= FPACE) mbar_wait(bar_box + (u - FPACE) * 8, 0);
          if (elect_one()) {
            if (u < 8) tma2d(dst, u < 4 ? &maps.wg : &maps.wu, b * 32, (u & 3) * 256, bar_box + u * 8);
            else tma3d(dst, &maps.wd, 0, b * 32, (u - 8) * 4, bar_box + u * 8);
          }
        }
      }
    } else if (warp == 9) {
      const uint32_t target = 8 * (epoch + 1);
#pragma unroll 1
      for (int i = 0; i < 16; i++) {
        if (i == HDX) mbar_wait(bar_mod, 0);
        if (i == NRS) {
          wait_counter(&g_cnt_h[rb * 32], target);
          PROF(1, lane == 0, 26);
          fence_async();
        }
        mbar_wait(xempty + (i & 3) * 8, ((i >> 2) & 1) ^ 1);
        if (elect_one()) {
          mbar_expect_tx(xfull + (i & 3) * 8, UNIT);
          if (i < NRS) tma2d(base + (i & 3) * GST_BYTES, &maps.x, ((2 * cj + i) & 15) * 64, rb * 128, xfull + (i & 3) * 8);
          else bulk_load_stream(base + (i & 3) * GST_BYTES, g_act + (uint32_t)(rb * 80 + ((2 * cj + i) & 15)) * UNIT, UNIT, xfull + (i & 3) * 8);
        }
      }
      prefetch_map(&maps.wo);
#pragma unroll 1
      for (int t = 0; t < 4; t++) {
        if (t & 1) mbar_wait(bar_od, t >> 1);
#pragma unroll 1
        for (int p = 0; p < 32768 / OPS; p++) {
          const uint32_t w = p / (16384 / OPS), c = (p / (8192 / OPS)) & 1, off = w * 8192 + (p % (8192 / OPS)) * OPS;
          mbar_wait(bar_ofull + (t & 1) * 16 + w * 8, t >> 1);
          if (elect_one()) {
            bulk_store(g_act + (uint32_t)(rb * 80 + 16 + (cj * 4 + t) * 2 + c) * UNIT + off, base + unit_of(QT, 2 * t + c) + off, OPS);
            asm volatile("cp.async.bulk.commit_group;" ::: "memory");
            asm volatile("cp.async.bulk.wait_group.read %0;" ::"n"(OFL) : "memory");
          }
        }
        if (elect_one()) {
          asm volatile("cp.async.bulk.wait_group.read 0;" ::: "memory");
          mbar_arrive_pred(bar_ofree + t * 8, t < 3);
          asm volatile("cp.async.bulk.wait_group 0;" ::: "memory");
          fence_async();
          red_release(&g_cnt_o[((rb * 4 + t) * 2 + (cj >> 2)) * 32], 2);
        }
        if (t & 1) {
          wait_counter(&g_cnt_o[(rb * 8 + 2 * t - 2 + (cj & 1)) * 32], target);
          wait_counter(&g_cnt_o[(rb * 8 + 2 * t + (cj & 1)) * 32], target);
          if (elect_one()) mbar_arrive_pred(bar_ofree + 24, t == 1);
        }
      }
      wait_counter(&g_cnt_o[(rb * 8 + 7 - (cj & 1)) * 32], target);
      fence_async();
      if (elect_one()) {
        mbar_arrive(bar_cnt);
        PROF(2, true, 27);
        mbar_expect_tx(bar_xres, 32768);
      }
#pragma unroll 1
      for (int u = 0; u < 2; u++) {
        mbar_wait(bar_res, u);
        if (elect_one()) tma2d(base + OFF_RES + u * UNIT, &maps.x, cj * 128 + u * 64, rb * 128, bar_xres);
      }
      const uint32_t tag = epoch % 3 + 1;
      const uint32_t* inbox = g_cand + (lane & 15);
      mbar_wait(bar_ring + 16, 0);
      uint32_t c0 = ld_relaxed(inbox), n = 0;
#define CAND_STEP(cv)                                                                                        \
      {                                                                                                      \
        const bool valid = (cv & 3u) == tag, all = __all_sync(0xffffffffu, valid);                           \
        const uint32_t best = __reduce_max_sync(0xffffffffu, valid ? cv : 0u);                               \
        const uint32_t blk = __ffs(__ballot_sync(0xffffffffu, cv == best)) - 1;                              \
        if (best) sts2(par + PAR_CONST + 56, best, (blk << 7 | (~best >> 2 & 127)) | (all ? 0x1800 : 0x800)); \
        if (all) break;                                                                                      \
        cv = ld_relaxed(inbox);                                                                              \
      }
      while (true) { CAND_STEP(c0) watchdog(n); }
    } else {
      const int t2 = tid - 320;
      if (t2 == 0) {
        mbar_wait(bar_hpub, 0);
        PROF(1, true, 24);
        red_release(&g_cnt_h[rb * 32], 1);
        PROF(1, true, 25);
        prefetch_map(&maps.wg); prefetch_map(&maps.wu); prefetch_map(&maps.wd); prefetch_map(&maps.out);
      }
      __syncwarp();
      if (b < NFFN) {
        mbar_wait(bar_go2, 0);
        const __nv_bfloat16* pg = ((b & 1) ? P.w_up : P.w_gate) + (b >> 1) * 64 + (size_t)t2 * FF;
        const __nv_bfloat16* pd = P.w_down + (size_t)b * 32768 + t2 * 64;
        PROF(2, t2 == 0, 13);
#pragma unroll 1
        for (int i = 0; i < WN; i += WB) {
          uint32_t v[WB];
#pragma unroll
          for (int u = 0; u < WB; u++) {
            const int k = i + u;
            asm volatile("ld.global.cg.L2::128B.u32 %0, [%1];" : "=r"(v[u]) : "l"(k < 16 ? pg + (size_t)k * 64 * FF : pd + (k - 16) * 4096));
          }
#pragma unroll
          for (int u = 1; u < WB; u++) v[0] ^= v[u];
          sts1(par + PAR_SINK + t2 * 4, v[0]);
        }
        PROF(2, t2 == 0, 14);
      }
      const uint32_t tag = epoch % 3 + 1;
      mbar_wait(bar_go, 0);
      if (warp == 10) {
        const uint32_t* src = g_mod + 2 * DM + cj * 128 + lane * 4;
        const uint2 wr = *reinterpret_cast<const uint2*>(P.w_r + cj * 128 + lane * 4);
        uint4 vga, vsb, vcb, vgb;
        uint32_t n = 0;
        do {
          vga = ld_relaxed4(src); vsb = ld_relaxed4(src + DM); vcb = ld_relaxed4(src + 2 * DM); vgb = ld_relaxed4(src + 3 * DM);
          watchdog(n);
        } while (!(tag_ok(vga, tag) && tag_ok(vsb, tag) && tag_ok(vcb, tag) && tag_ok(vgb, tag)));
        const float c0 = rbf(1.f + bf_hi(vcb.x)), c1 = rbf(1.f + bf_hi(vcb.y)), c2 = rbf(1.f + bf_hi(vcb.z)), c3 = rbf(1.f + bf_hi(vcb.w));
        const float a0 = c0 * bf_lo(wr.x), a1 = c1 * bf_hi(wr.x), a2 = c2 * bf_lo(wr.y), a3 = c3 * bf_hi(wr.y);
        const uint32_t h0 = pack_bf(a0, a1), h1 = pack_bf(a2, a3);
        const uint32_t t1 = par + PAR_T1 + (lane >> 2) * 64 + (lane & 1) * 32 + (lane & 2) * 2;
        sts1(t1, h0); sts1(t1 + 8, pack_bf(a0 - bf_lo(h0), a1 - bf_hi(h0)));
        sts1(t1 + 16, h1); sts1(t1 + 24, pack_bf(a2 - bf_lo(h1), a3 - bf_hi(h1)));
        sts4(par + PAR_T2 + lane * 32, make_uint4(pack_bf(c0, c1), __byte_perm(vsb.x, vsb.y, 0x7632), __byte_perm(vgb.x, vgb.y, 0x7632), __byte_perm(vga.x, vga.y, 0x7632)));
        sts4(par + PAR_T2 + lane * 32 + 16, make_uint4(pack_bf(c2, c3), __byte_perm(vsb.z, vsb.w, 0x7632), __byte_perm(vgb.z, vgb.w, 0x7632), __byte_perm(vga.z, vga.w, 0x7632)));
      } else if (lane < 4) {
        const uint4 g = poll4(lane < 2 ? g_mod + 5 * DM + b * 8 + lane * 4 : g_mod + 16 - lane * 4, tag);
        sts1(par + PAR_CONST + 60, 0);
        if (lane < 2) sts4(par + PAR_CONST + 16 + lane * 16, g);
        else sts2(par + PAR_CONST + (lane - 2) * 8, __float_as_uint(untag_sum(g.x, g.y) + untag_sum(g.z, g.w)), epoch);
      }
      __syncwarp();
#pragma unroll 4
      for (int q = XR; q < XE; q++) st_b128(g_xch + ((size_t)b * 8 * 256 + q * 64 + t2) * 4, (epoch & 1) << 16, 0, 0, 0);
      for (int q = 0; q < 2; q++) st_relaxed4(g_stats + ((size_t)cj * SEQ + rb * 128 + q * 64 + t2) * 4, 0, 0, 0, 0);
      if (b < NFFN)
        for (int q = 0; q < 4; q++) st_relaxed4(g_ypart + ((size_t)(q * 32 + (t2 >> 1)) * NFFN + b) * 8 + (t2 & 1) * 4, 0, 0, 0, 0);
      st_relaxed4(g_row + rb * 2 * DM + (t2 >> 5) * DM + cj * 128 + (t2 & 31) * 4, 0, 0, 0, 0);
      __threadfence();
      mbar_arrive(bar_par);
      mbar_wait(bar_gate, 0);
      uint32_t have = 0, n = 0;
      while (true) {
        const uint32_t st = lds1(par + PAR_CONST + 60) >> 7;
        if ((st & 31) != have) {
          const uint32_t* hsrc = g_row + (st & 15) * 2 * DM + t2 * 4;
          uint4 hv[4];
          bool ok = true;
#pragma unroll
          for (int i = 0; i < 4; i++) hv[i] = ld_pairs(hsrc + i * 256);
#pragma unroll
          for (int i = 0; i < 4; i++) {
            sts2(base + ((FT_G >> i * 4) & 15) * UNIT + (warp & 1) * 8192 + 256 + lane * 8, hv[i].x, hv[i].z);
            ok = ok && hv[i].y == tag && hv[i].w == tag;
          }
          have = __all_sync(0xffffffffu, ok) ? st & 31 : 0;
        }
        if ((st ^ have) == 32) break;
        watchdog(n);
      }
      mbar_arrive(bar_sel);
    }
    __syncwarp();
    cluster_arrive();
    {
      const uint32_t tag = epoch % 3 + 1, t3 = tid - 256;
      mbar_wait(bar_win, 0);
      uint2 win = lds2(par + PAR_CONST + 56);
      win.y &= 0x7ff;
      const uint32_t* fsrc = g_row + (win.y >> 7) * 2 * DM + (b >> 1) * 16 + (t3 & 3) * 4 + (b & 1) * 2;
      const uint32_t* ysrc = g_ypart + (size_t)b * NFFN * 8 + min(t3, NFFN - 1) * 4;
      uint2 fh = ld_pair(fsrc), fx = ld_pair(fsrc + DM);
      if (PSL) __nanosleep(PSL);
      uint4 ya = ld_relaxed4(ysrc), yb = ld_relaxed4(ysrc + NFFN * 4);
      const float rwin = __uint_as_float(((int)win.x < 0 ? win.x & 0x7fffffffu : ~win.x) & ~0x1ffu);
      const float rs = rbf(rcp(1.f + __expf(-rbf(rwin))));
      uint32_t n = 0;
      while (fh.y != tag || fx.y != tag) { fh = ld_pair(fsrc); fx = ld_pair(fsrc + DM); watchdog(n); }
      while (!(tag_ok(ya, tag) && tag_ok(yb, tag))) {
        if (!tag_ok(ya, tag)) ya = ld_relaxed4(ysrc);
        if (!tag_ok(yb, tag)) yb = ld_relaxed4(ysrc + NFFN * 4);
        watchdog(n);
      }
      __syncwarp();
      PROF(8, t3 == 0, 5);
      float y0 = untag_sum(ya.x, yb.x), y1 = untag_sum(ya.y, yb.y), y2 = untag_sum(ya.z, yb.z), y3 = untag_sum(ya.w, yb.w);
      const bool u1 = lane & 2, u2 = lane & 4;
      y0 = (u1 ? y2 : y0) + __shfl_xor_sync(0xffffffffu, u1 ? y0 : y2, 2);
      y1 = (u1 ? y3 : y1) + __shfl_xor_sync(0xffffffffu, u1 ? y1 : y3, 2);
      y0 = (u2 ? y1 : y0) + __shfl_xor_sync(0xffffffffu, u2 ? y0 : y1, 4);
      y0 += __shfl_xor_sync(0xffffffffu, y0, 8);
      if (!(lane & 8)) sts1(par + PAR_RED + 64 + (t3 >> 4) * 32 + ((lane & 1) * 4 + (lane & 2) + ((lane >> 2) & 1)) * 4, __float_as_uint(y0));
      bar_sync(4, 128);
      if (t3 < 4) {
        y0 = 0.f; y1 = 0.f;
#pragma unroll
        for (int w4 = 0; w4 < 7; w4++) {
          const uint2 v = lds2(par + PAR_RED + 64 + w4 * 32 + t3 * 8);
          y0 += __uint_as_float(v.x); y1 += __uint_as_float(v.y);
        }
        const uint2 gv = lds2(par + PAR_CONST + 16 + t3 * 8);
        const uint32_t upd = hmul2(pack_bf(y0, y1), pack_bf(rs, rs));
        *reinterpret_cast<uint32_t*>(P.out + (size_t)win.y * DM + b * 8 + t3 * 2) =
            hadd2(fx.x, hmul2(__byte_perm(gv.x, gv.y, 0x7632), hadd2(fh.x, upd)));
        if (b == 0 && t3 == 0) st_relaxed(&g_epoch, epoch + 1);
      }
      PROF(31, t3 == 0, 36);
    }
    cluster_wait();
  } else {
    const int wg = warp >> 2;

    uint32_t tag;
    {
      uint32_t* const pmod = g_modp + rank * 2 * DM + (b >> 1) * 32 + lane;
      uint32_t* const pln = g_ln1 + (rb * 128 + cj * 16 + warp) * 4;
      const uint32_t cv = ldg_nc1(P.c + rank * 512 + tid * 2);
      const uint32_t epoch = ld_relaxed(&g_epoch);
      if (warp == 0) st_relaxed(pmod, 0);
      if (lane == 0) { st_relaxed2(pln, 0, 0); st_relaxed2(pln + 32, 0, 0); }
      asm volatile("setmaxnreg.inc.sync.aligned.u32 232;");
      sts1(par + tid * 4, pack_bf(silu_f(bf_lo(cv)), silu_f(bf_hi(cv))));
      bar_sync(1, 320);
      tag = epoch % 3 + 1;
#pragma unroll
      for (int part = 0; part < 3; part++) {
        if (part != 1) {
          const uint32_t xa = base + (2 + part / 2) * GST_BYTES + warp * 2048 + lane * 16;
          mbar_wait(bar_hx + part * 4, 0);
          float s0 = 0.f, s1 = 0.f, q0 = 0.f, q1 = 0.f;
#pragma unroll
          for (int q = 0; q < 4; q++) {
            const uint4 xv = lds4(xa + q * 512);
            const uint32_t u[4] = {xv.x, xv.y, xv.z, xv.w};
#pragma unroll
            for (int e = 0; e < 4; e++) { const float lo = bf_lo(u[e]), hi = bf_hi(u[e]); s0 += lo; s1 += hi; q0 += lo * lo; q1 += hi * hi; }
          }
          s0 += s1; q0 += q1;
#pragma unroll
          for (int o = 16; o > 0; o >>= 1) { s0 += __shfl_xor_sync(0xffffffffu, s0, o); q0 += __shfl_xor_sync(0xffffffffu, q0, o); }
          const float mean = s0 * (1.f / DM);
          float mb, sd;
          ln_scalars(mean, fmaxf(q0 * (1.f / DM) - mean * mean, 0.f), mb, sd);
          if (lane == 0) st_relaxed2(pln + part * 16, __float_as_uint(mb) | tag, __float_as_uint(sd) | tag);
          PROF(1, tid == 0 && part == 2, 4);
        } else {
          float acc[8];
#pragma unroll
          for (int e = 0; e < 8; e++) acc[e] = 0.f;
          const uint32_t wa = stage + (tid >> 2) * 64 + (((tid ^ (tid >> 3)) & 3) << 4), sa = par + (tid >> 3) * 4, sh = (tid & 4) ? 0x3244 : 0x1044;
          mbar_wait(bar_hw, 0);
#pragma unroll
          for (int p = 0; p < 8; p++) {
            const uint4 w = lds4(wa + p * 4096);
            const float s = __uint_as_float(__byte_perm(lds1(sa + p * 128), 0, sh));
            acc[0] += s * bf_lo(w.x); acc[1] += s * bf_hi(w.x); acc[2] += s * bf_lo(w.y); acc[3] += s * bf_hi(w.y);
            acc[4] += s * bf_lo(w.z); acc[5] += s * bf_hi(w.z); acc[6] += s * bf_lo(w.w); acc[7] += s * bf_hi(w.w);
          }
#pragma unroll
          for (int e = 0; e < 4; e++) {
            const bool up = lane & 16;
            acc[e] = (up ? acc[e + 4] : acc[e]) + __shfl_xor_sync(0xffffffffu, up ? acc[e] : acc[e + 4], 16);
          }
#pragma unroll
          for (int e = 0; e < 2; e++) {
            const bool up = lane & 8;
            acc[e] = (up ? acc[e + 2] : acc[e]) + __shfl_xor_sync(0xffffffffu, up ? acc[e] : acc[e + 2], 8);
          }
          {
            const bool up = lane & 4;
            acc[0] = (up ? acc[1] : acc[0]) + __shfl_xor_sync(0xffffffffu, up ? acc[0] : acc[1], 4);
          }
          sts1(par + 1024 + warp * 128 + ((lane & 3) * 8 + (lane >> 2)) * 4, __float_as_uint(acc[0]));
          bar_sync(1, 256);
          if (warp == 0) {
            float s = 0.f;
#pragma unroll
            for (int w8 = 0; w8 < 8; w8++) s += __uint_as_float(lds1(par + 1024 + w8 * 128 + lane * 4));
            st_relaxed(pmod, (__float_as_uint(s) & ~3u) | tag);
          }
          PROF(1, tid == 0, 3);
        }
      }
      {
        uint2 s0 = ld_relaxed2(g_ln1 + (rb * 128 + (tid & 127)) * 4);
        uint4 v[4];
#pragma unroll
        for (int q = 0; q < 4; q++) v[q] = ld_relaxed4(g_modp + q * DM + tid * 4);
        {
          uint32_t n = 0;
          while (!(tag_ok(v[0], tag) && tag_ok(v[1], tag) && tag_ok(v[2], tag) && tag_ok(v[3], tag))) {
#pragma unroll
            for (int q = 0; q < 4; q++)
              if (!tag_ok(v[q], tag)) v[q] = ld_relaxed4(g_modp + q * DM + tid * 4);
            if (((s0.x ^ tag) | (s0.y ^ tag)) & 3u) s0 = ld_relaxed2(g_ln1 + (rb * 128 + (tid & 127)) * 4);
            watchdog(n);
          }
        }
        const uint32_t d = stage + (tid >> 2) * 64 + (tid & 1) * 32 + (tid & 2) * 2;
        sts1(d, pack_bf(1.f + rbf(untag_sum(v[1].x, v[3].x)), 1.f + rbf(untag_sum(v[1].y, v[3].y))));
        sts1(d + 16, pack_bf(1.f + rbf(untag_sum(v[1].z, v[3].z)), 1.f + rbf(untag_sum(v[1].w, v[3].w))));
        sts1(d + 8, pack_bf(untag_sum(v[0].x, v[2].x), untag_sum(v[0].y, v[2].y)));
        sts1(d + 24, pack_bf(untag_sum(v[0].z, v[2].z), untag_sum(v[0].w, v[2].w)));
        if (wg == 0) {
          uint32_t n = 0;
          while (((s0.x ^ tag) | (s0.y ^ tag)) & 3u) { s0 = ld_relaxed2(g_ln1 + (rb * 128 + tid) * 4); watchdog(n); }
          uint32_t ih, il;
          split_inv(bf_hi(s0.y), ih, il);
          sts4(stage + 4096 + tid * 16, make_uint4(__byte_perm(s0.x, 0, 0x3232), ih, il, 0));
        }
        mbar_arrive(bar_mod);
      }
      cluster_wait();
      if (wg == 1) bar_arrive(2, 256);
      mbar_wait(bar_mod, 0);
      PROF(1, tid == 0, 2);
    }

    float f0 = 0.f, f1 = 0.f;
    const uint32_t rempty = lane < 2 ? mapa(bempty, lane & 1) : 0;
    constexpr uint32_t GE = NSLOT * 8 + 32;
    float o[64], s[64];
#pragma unroll 1
    for (int ps = 0; ps < 3; ps++) {
      {
        const uint32_t xt = ps == 1 ? XT1 : XT2, wt = ps == 1 ? WT1 : WT2;
        const int nst = ps == 2 ? 28 : 14;
        if (ps == 0) {
          float ga[64], gb[64];
#pragma unroll
          for (int i = 0; i < 64; i++) { ga[i] = 0.f; gb[i] = 0.f; }
          uint32_t a[2][16];
          const uint32_t l = fresh_lane();
          const uint4 r0 = lds4(stage + 4096 + (warp * 16 + (l >> 2)) * 16), r1 = lds4(stage + 4096 + 128 + (warp * 16 + (l >> 2)) * 16);
          auto transform = [&](int i, uint32_t (&f)[16], uint32_t z) {
            const uint32_t ad = base + (i & 3) * GST_BYTES + wg * 8192 + frag_offset(warp) + z;
            mbar_wait(xfull + (i & 3) * 8, i >> 2);
#pragma unroll
            for (int kk = 0; kk < 4; kk++) ldmatrix4(ad ^ (kk * 32), f[4 * kk], f[4 * kk + 1], f[4 * kk + 2], f[4 * kk + 3]);
#pragma unroll
            for (int kk = 0; kk < 4; kk++) {
              const uint4 m = lds4(stage + (l & 3) * 16 + ((2 * cj + i) & 15) * 256 + kk * 64);
              f[4 * kk] = ln_mod(f[4 * kk], r0.x, r0.y, r0.z, m.x, m.z);
              f[4 * kk + 1] = ln_mod(f[4 * kk + 1], r1.x, r1.y, r1.z, m.x, m.z);
              f[4 * kk + 2] = ln_mod(f[4 * kk + 2], r0.x, r0.y, r0.z, m.y, m.w);
              f[4 * kk + 3] = ln_mod(f[4 * kk + 3], r1.x, r1.y, r1.z, m.y, m.w);
            }
            keep(f);
            mbar_arrive_pred(xempty + (i & 3) * 8, l == 0);
          };
          auto publish = [&](int u, uint32_t (&f)[16]) {
            const uint32_t sc = stage + 8192 + wg * 8192;
#pragma unroll
            for (int kk = 0; kk < 4; kk++) stmatrix4((sc + frag_offset(warp)) ^ (kk * 32), f[4 * kk], f[4 * kk + 1], f[4 * kk + 2], f[4 * kk + 3]);
            __syncwarp();
            const uint32_t src = sc + (warp & 3) * 2048 + l * 16;
            uint8_t* dst = g_act + (uint32_t)(rb * 80 + cj * 2 + u) * UNIT + warp * 2048 + l * 16;
#pragma unroll
            for (int p4 = 0; p4 < 4; p4++) stg4(dst + p4 * 512, lds4(src + p4 * 512));
            __syncwarp();
            if (u == 1) mbar_arrive_pred(bar_hpub, l == 0);
          };
          auto multiply = [&](int i, uint32_t (&f)[16]) {
            mbar_wait(gfull + (i & 3) * 8, i >> 2);
            const uint64_t db = make_desc(base + (i & 3) * GST_BYTES + UNIT, 8192, 1024);
            wg_fence();
#pragma unroll
            for (int kk = 0; kk < 4; kk++) mma256_rs(ga, gb, f[4 * kk], f[4 * kk + 1], f[4 * kk + 2], f[4 * kk + 3], db + kk * 128);
            wg_commit();
          };
          transform(0, a[0], 0); publish(0, a[0]); transform(1, a[1], 0); multiply(0, a[0]); publish(1, a[1]);
#pragma unroll
          for (int i = 1; i < NRS; i++) {
            if (i >= 2) {
              uint32_t z = r0.w;
#pragma unroll
              for (int k = 0; k < 16; k += 2) asm volatile("lop3.b32 %0, %1, %2, %0, 0xA8;" : "+r"(z) : "r"(a[i & 1][k]), "r"(a[i & 1][k + 1]));
              transform(i, a[i & 1], z);
            }
            multiply(i, a[i & 1]);
            wg_wait<1>();
            mbar_arrive_cl(rempty, GE + ((i + 3) & 3) * 8);
          }
          mbar_arrive_pred(bar_pread, l == 0);
#pragma unroll 1
          for (int i = NRS; i < 14; i++) {
            mbar_wait(xfull + (i & 3) * 8, (i >> 2) & 1);
            mbar_wait(gfull + (i & 3) * 8, (i >> 2) & 1);
            const uint32_t xa = base + (i & 3) * GST_BYTES;
            const uint64_t da = make_desc(xa + wg * 8192, 16, 1024), db = make_desc(xa + UNIT, 8192, 1024);
            if (i == 13) bar_sync(2 + wg, 256);
            wg_fence();
#pragma unroll
            for (int kk = 0; kk < 4; kk++) mma256_ss(ga, gb, da + kk * 2, db + kk * 128, 1);
            wg_commit();
            if (i == 13) bar_arrive(3 - wg, 256);
            wg_wait<1>();
            uint32_t z = r0.w;
#pragma unroll
            for (int k = 0; k < 16; k += 2) asm volatile("lop3.b32 %0, %1, %2, %0, 0xA8;" : "+r"(z) : "r"(a[1][k]), "r"(a[1][k + 1]));
            mbar_arrive_cl(rempty, GE + ((i + 3) & 3) * 8 + z);
            mbar_arrive_pred(xempty + ((i + 3) & 3) * 8, l == 0 && i != NRS);
          }
          mbar_wait(xfull + 16, 1);
          wg_wait<0>();
          keep(ga); keep(gb);
#pragma unroll
          for (int i = 0; i < 64; i++) {
            asm volatile("mov.b32 %0, %1;" : "=f"(s[i]) : "f"(ga[i]));
            asm volatile("mov.b32 %0, %1;" : "=f"(o[i]) : "f"(gb[i]));
          }
        } else {
          float ga[64], gb[64];
#pragma unroll
          for (int i = 0; i < 64; i++) {
            asm volatile("mov.b32 %0, %1;" : "=f"(ga[i]) : "f"(s[i]));
            asm volatile("mov.b32 %0, %1;" : "=f"(gb[i]) : "f"(o[i]));
          }
#pragma unroll 1
          for (int i = 0; i < nst; i++) {
            mbar_wait(gfull + (i & 3) * 8, (i >> 2) & 1);
            const uint64_t da = make_desc(base + unit_of(xt, i & 3) + wg * 8192, 16, 1024), db = make_desc(base + unit_of(wt, i & 3), 8192, 1024);
            if (i == nst - 1) bar_sync(2 + wg, 256);
            wg_fence();
#pragma unroll
            for (int kk = 0; kk < 4; kk++) mma256_ss(ga, gb, da + kk * 2, db + kk * 128, kk ? 1 : i);
            wg_commit();
            if (i == nst - 1) bar_arrive(3 - wg, 256);
            wg_wait<1>();
            mbar_arrive_cl(rempty, GE + ((i + 3) & 3) * 8, i != 0);
            PROF(4, tid == 0 && (i & 3) == 0, 40 + (ps - 1) * 4 + i / 4);
          }
          wg_wait<0>();
          keep(ga); keep(gb);
#pragma unroll
          for (int i = 0; i < 64; i++) {
            asm volatile("mov.b32 %0, %1;" : "=f"(s[i]) : "f"(ga[i]));
            asm volatile("mov.b32 %0, %1;" : "=f"(o[i]) : "f"(gb[i]));
          }
        }
        mbar_arrive_cl(rempty, GE + (ps == 2 ? 24 : 8));
        if (ps == 2) break;
      }
      const uint32_t qw = base + wg * 8192, qt = QT >> (16 * ps), at = ps ? AT1 : AT0;
      {
        const uint32_t wt = ps ? WT1 : WT0;
        const uint64_t da0 = make_desc(qw + unit_of(qt, 2), 16, 1024), da1 = make_desc(qw + unit_of(qt, 3), 16, 1024);
        const uint64_t db0 = make_desc(base + unit_of(wt, 2), 8192, 1024), db1 = make_desc(base + unit_of(wt, 3), 8192, 1024);
        mbar_wait(gfull + 16, 1);
        bar_sync(2 + wg, 256);
        wg_fence();
#pragma unroll
        for (int kk = 0; kk < 4; kk++) mma_ss<1>(s, da0 + kk * 2, db0 + kk * 128, 1);
        wg_commit();
        mbar_wait(xfull + 24, 1);
        mbar_wait(gfull + 24, 1);
        wg_fence();
#pragma unroll
        for (int kk = 0; kk < 4; kk++) mma_ss<1>(s, da1 + kk * 2, db1 + kk * 128, 1);
        wg_commit();
        bar_arrive(3 - wg, 256);
        mbar_wait(ps == 0 ? bar_pread : bar_ofree + 8, 0);
        mbar_wait(bfull, 0);
        wg_wait<0>();
        keep(s);
        PROF(2, tid == 0, 8 + ps * 8);
        store_chunk<0>(s, qw + unit_of(qt, 0) + frag_offset(warp));
        store_chunk<1>(s, qw + unit_of(qt, 1) + frag_offset(warp));
        fence_async_smem();
        bar_sync(2 + wg, 256);
        wg_fence();
        issue_qk(s, qw + unit_of(qt, 0), qw + unit_of(qt, 1), base + unit_of(at, 0));
        wg_commit();
#pragma unroll
        for (int kk = 0; kk < 8; kk++) mma_ss<1>(o, (kk < 4 ? da0 : da1) + (kk & 3) * 2, (kk < 4 ? db0 : db1) + UNIT / 16 + (kk & 3) * 128, 1);
        wg_commit();
        bar_arrive(3 - wg, 256);
        wg_wait<1>();
        keep(s);
        mbar_arrive_cl(rempty, 0);
      }
      PROF(4, tid == 0 && ps == 1, 61);
      float l0 = 0.25f, l1 = 0.25f;
      auto step = [&](auto odd_c, const int j, uint32_t (&pw)[32], uint32_t (&pr)[32]) {
        constexpr bool ODD = decltype(odd_c)::value;
        const bool first = !ODD && (j & 2) == 0, last = ODD && j == 7;
        const uint32_t ph = (j >> 1) & 1;
        float i0, i1, a0, a1;
        if (first) { i0 = inv_quad_sum(l0); i1 = inv_quad_sum(l1); l0 = 0.f; l1 = 0.f; }
        bool redo = !ODD && (j | ps) == 0, again = false;
        while (true) {
          if (redo) {
            float m0 = fmaxf(s[0], s[1]), m1 = fmaxf(s[2], s[3]);
#pragma unroll
            for (int i = 1; i < 16; i++) { m0 = fmaxf(m0, fmaxf(s[4 * i], s[4 * i + 1])); m1 = fmaxf(m1, fmaxf(s[4 * i + 2], s[4 * i + 3])); }
            m0 = fmaxf(m0, __shfl_xor_sync(0xffffffffu, m0, 1)); m1 = fmaxf(m1, __shfl_xor_sync(0xffffffffu, m1, 1));
            m0 = fmaxf(m0, __shfl_xor_sync(0xffffffffu, m0, 2)); m1 = fmaxf(m1, __shfl_xor_sync(0xffffffffu, m1, 2));
            m0 *= SCL2; m1 *= SCL2;
            if (!first) {
              m0 = fmaxf(m0, f0); m1 = fmaxf(m1, f1);
              const float c0 = ex2(f0 - m0), c1 = ex2(f1 - m1);
              l0 *= c0; l1 *= c1;
              wg_wait<0>();
              keep(o);
#pragma unroll
              for (int i = 0; i < 16; i++) { o[4 * i] *= c0; o[4 * i + 1] *= c0; o[4 * i + 2] *= c1; o[4 * i + 3] *= c1; }
            }
            f0 = m0; f1 = m1;
          }
          float b0 = 0.f, b1 = 0.f;
          a0 = 0.f; a1 = 0.f;
#pragma unroll
          for (int i = 0; i < 16; i++) {
            const float e0 = ex2(fmaf(s[4 * i], SCL2, -f0)), e1 = ex2(fmaf(s[4 * i + 1], SCL2, -f0));
            const float e2 = ex2(fmaf(s[4 * i + 2], SCL2, -f1)), e3 = ex2(fmaf(s[4 * i + 3], SCL2, -f1));
            a0 += e0; b0 += e1; a1 += e2; b1 += e3;
            pw[2 * i] = pack_bf(e0, e1); pw[2 * i + 1] = pack_bf(e2, e3);
            if (i == VREL) {
#pragma unroll
              for (int k = 0; k < 2 * VREL + 2; k++) asm volatile("" : "+r"(pw[k])::"memory");
              mbar_wait(bar_mod, 0);
              wg_wait<0>();
              mbar_arrive_cl(rempty, ODD ? 16 : (j ? 0 : GE + 16), !again);
              if (!ODD) mbar_arrive_cl(rempty, GE + 24, !again && j == 0);
#pragma unroll
              for (int k = 4 * VREL + 4; k < 64; k++) asm volatile("" : "+f"(s[k])::"memory");
            }
          }
          a0 += b0; a1 += b1;
          if (redo) break;
          redo = __any_sync(0xffffffffu, !(a0 + a1 < 0x1p70f));
          if (first) {
            uint32_t m0 = __ballot_sync(0xffffffffu, a0 > 0x1p-50f), m1 = __ballot_sync(0xffffffffu, a1 > 0x1p-50f);
            m0 |= m0 >> 1; m1 |= m1 >> 1; m0 |= m0 >> 2; m1 |= m1 >> 2;
            redo = redo || (m0 & m1 & 0x11111111u) != 0x11111111u;
          }
          if (!redo) break;
          again = true;
        }
        l0 += a0; l1 += a1;
        keep(pw);
        keep(o);
        const uint32_t qo = qt >> (j ? 0 : 8);
        if (first) store_chunk<0>(o, i0, i1, qw + unit_of(qo, 0) + frag_offset(warp));
        keep(o);
        mbar_wait(bfull + (ODD ? 24 : 8), ph);
        bar_sync(2 + wg, 256);
        if (!last) {
          const uint32_t qn = qt >> (j >= 3 ? 8 : 0);
          wg_fence();
          issue_qk(s, qw + unit_of(qn, 0), qw + unit_of(qn, 1), base + unit_of(at, ODD ? 3 : 1));
          wg_commit();
          mbar_wait(bfull + (ODD ? 0 : 16), ODD ? ph ^ 1 : ph);
        }
        if (first) { store_chunk<1>(o, i0, i1, qw + unit_of(qo, 1) + frag_offset(warp)); keep(o); }
        wg_fence();
        issue_pv(o, pw, base + unit_of(at, ODD ? (last ? 3 : 0) : 2), !first);
        wg_commit();
        bar_arrive(3 - wg, 256);
        wg_wait<1>();
        keep(s);
        mbar_arrive_cl(rempty, ODD ? 24 : 8, !last);
        if (first) { fence_async_smem(); mbar_arrive_pred(bar_ofull + wg * 8, j); }
        PROF(4, tid == 0 && ps == 1, 51 + j);
      };
      uint32_t pa[32], pb[32];
#pragma unroll 1
      for (int j = 0; j < 8; j += 2) {
        step(std::false_type{}, j, pa, pb);
        step(std::true_type{}, j + 1, pb, pa);
      }
      {
        const float i0 = inv_quad_sum(l0), i1 = inv_quad_sum(l1);
        wg_wait<0>();
        keep(o);
        mbar_arrive_cl(rempty, 24);
        store_chunk<0>(o, i0, i1, qw + unit_of(qt, 2) + frag_offset(warp));
        store_chunk<1>(o, i0, i1, qw + unit_of(qt, 3) + frag_offset(warp));
        fence_async_smem();
        mbar_arrive(bar_ofull + 16 + wg * 8);
      }
      PROF(2, tid == 0, 10 + ps * 8);
    }

    const int ln = fresh_lane(), g = ln >> 2, tq = ln & 3, ct = warp * 32 + ln;
    const bool lane0 = ln == 0;
    const int lrow0 = warp * 16 + g;
    const int grow0 = rb * 128 + lrow0;
    const uint32_t res = base + OFF_RES, trow = res + wg * 8192 + frag_offset(warp);
    uint32_t xr[32];
    uint4 sv[4], own;
    uint32_t* sp[4];
#pragma unroll
    for (int k = 0; k < 4; k++) sp[k] = g_stats + ((((tq >> 1) * 4 + k) ^ cj) * SEQ + grow0 + (tq & 1) * 8) * 4;
    {
      const uint64_t da = make_desc(base + wg * 8192, 16, 1024), db = make_desc(base, 8192, 1024);
      constexpr int U = UNIT / 16;
#define HALF_STAGE(acc, xu, wu) _Pragma("unroll") for (int kk = 0; kk < 4; kk++) mma_ss<1>(acc, da + (xu) * U + kk * 2, db + (wu) * U + kk * 128, 1)
      PROF(10, ct == PT, 19); STAMP(0);
      cluster_arrive();
      mbar_wait(gfull, 1);
      mbar_wait(gfull + 8, 1);
      bar_sync(2 + wg, 256);
      wg_fence();
      HALF_STAGE(o, 7, 1);
      HALF_STAGE(o, 8, 3);
      wg_commit();
      STAMP(16);
      mbar_wait(gfull + 16, 1);
      STAMP(17);
      wg_fence();
      HALF_STAGE(o, 6, 11);
      wg_commit();
      bar_arrive(3 - wg, 256);
      mbar_wait(bar_par, 0);
      uint32_t* xo = g_xch + ((size_t)b * 8 * 256 + ct) * 4;
      const uint32_t* xi = g_xch + ((size_t)(b ^ 2) * 8 * 256 + ct) * 4;
      const uint32_t par1 = (~lds1(par + PAR_CONST + 4) & 1) << 16;
      uint32_t ga[16];
      uint4 bw[8];
#define LOAD_PAR _Pragma("unroll") for (int i = 0; i < 8; i++) {                                                               \
        ga[2 * i] = lds1(par + PAR_T2 + i * 128 + tq * 16 + 12); ga[2 * i + 1] = lds1(par + PAR_T2 + i * 128 + 64 + tq * 16 + 12); \
        bw[i] = lds4(par + PAR_T1 + i * 64 + tq * 16);                                                                          \
        if (!(g & 1)) { bw[i].x = 0x3f803f80u; bw[i].y = 0x3f803f80u; }                                                         \
      }
      if (PPOS == 0) LOAD_PAR
      wg_wait<1>();
      mbar_arrive_pred(bar_rel, lane0);
      wg_wait<0>();
      keep(o);
      mbar_arrive_pred(bar_ring, lane0);
      PROF(8, ct == PT, 20); STAMP(1);
#define SEND(i) st_b128(xo + (i) * 1024, (pack_bf(o[8 * (i)], o[8 * (i) + 1]) & ~0x10000u) | par1, pack_bf(o[8 * (i) + 2], o[8 * (i) + 3]), \
                        pack_bf(o[8 * (i) + 4], o[8 * (i) + 5]), pack_bf(o[8 * (i) + 6], o[8 * (i) + 7]))
#pragma unroll
      for (int i = 0; i < NS1; i++) SEND(i);
      PROF(8, ct == PT, 21); STAMP(2);
      bar_sync(2 + wg, 256);
      wg_fence();
      HALF_STAGE(s, 7, 0);
      HALF_STAGE(s, 8, 2);
      HALF_STAGE(s, 6, 10);
      wg_commit();
      bar_arrive(3 - wg, 256);
      STAMP(18);
      mbar_wait(gfull + 24, 1);
#pragma unroll
      for (int i = NS1; i < 8; i++) SEND(i);
      uint4 v[8];
#pragma unroll
      for (int i = 0; i < 4; i++) v[i] = ld_b128(xi + i * 1024);
      if (PPOS == 1) LOAD_PAR
      STAMP(19);
      mbar_wait(bar_xres, 0);
      wg_wait<0>();
      mbar_arrive_pred(bar_ring + 8, lane0);
      bar_sync(2 + wg, 256);
      STAMP(20);
#pragma unroll
      for (int i = 4; i < 8; i++) v[i] = ld_b128(xi + i * 1024);
      mbar_wait(bar_xres, 0);
      wg_fence();
      HALF_STAGE(s, 9, 4);
      wg_commit();
      mbar_wait(bar_rx, 0);
      wg_fence();
      HALF_STAGE(s, 1, 5);
      wg_commit();
      bar_arrive(3 - wg, 256);
      STAMP(21);
      wg_wait<0>();
      keep(s);
      mbar_arrive_pred(bar_ring + 16, lane0);
      PROF(10, ct == PT, 23); STAMP(4);
#pragma unroll
      for (int i = 0; i < 16; i += 2) ldmatrix4((trow ^ ((i & 7) << 4)) + (i >> 3) * 16384, xr[2 * i], xr[2 * i + 1], xr[2 * i + 2], xr[2 * i + 3]);
      if (PPOS == 2) LOAD_PAR
      uint32_t pk[32];
      pack_p(s, pk);
      keep(pk);
      {
        uint32_t n = 0;
        bool ok;
        do {
          ok = true;
#pragma unroll
          for (int i = 0; i < 8; i++)
            if ((v[i].x & 0x10000u) != par1) { v[i] = ld_b128(xi + i * 1024); ok = false; }
          watchdog(n);
        } while (!ok);
      }
      __syncwarp();
      PROF(8, ct == PT, 22); STAMP(3);
#pragma unroll
      for (int k = 0; k < 4; k++) sv[k] = ESV ? ld_b128(sp[k]) : make_uint4(0, 0, 0, 0);
      float ds[4] = {0.f, 0.f, 0.f, 0.f}, dl[4] = {0.f, 0.f, 0.f, 0.f}, q0[4] = {0.f, 0.f, 0.f, 0.f}, q1[4] = {0.f, 0.f, 0.f, 0.f};
#pragma unroll
      for (int i = 0; i < 8; i++) {
        const uint32_t u0 = hfma2(ga[2 * i], hadd2(pk[4 * i], v[i].x & ~0x10000u), xr[4 * i]);
        const uint32_t u1 = hfma2(ga[2 * i], hadd2(pk[4 * i + 1], v[i].y), xr[4 * i + 1]);
        const uint32_t u2 = hfma2(ga[2 * i + 1], hadd2(pk[4 * i + 2], v[i].z), xr[4 * i + 2]);
        const uint32_t u3 = hfma2(ga[2 * i + 1], hadd2(pk[4 * i + 3], v[i].w), xr[4 * i + 3]);
        xr[4 * i] = u0; xr[4 * i + 1] = u1; xr[4 * i + 2] = u2; xr[4 * i + 3] = u3;
        mma16816(ds, u0, u1, u2, u3, bw[i].x, bw[i].y);
        mma16816(dl, u0, u1, u2, u3, bw[i].z, bw[i].w);
        mma16816(q0, u0, u1, u2, u3, u0, u2);
        mma16816(q1, u0, u1, u2, u3, u1, u3);
      }
      const float sqa = __shfl_sync(0xffffffffu, (g & 1) ? q0[1] : q0[0], g * 4 + (g >> 1));
      const float sqb = __shfl_sync(0xffffffffu, (g & 1) ? q1[3] : q1[2], g * 4 + (g >> 1));
      own = (tq & 1) ? make_uint4(__float_as_uint(ds[2]), __float_as_uint(sqb), __float_as_uint(ds[3] + dl[3]), tag)
                                 : make_uint4(__float_as_uint(ds[0]), __float_as_uint(sqa), __float_as_uint(ds[1] + dl[1]), tag);
      if (tq < 2) st_b128(sp[0], own.x, own.y, own.z, own.w);
    }
    PROF(8, ct == PT, 29); STAMP(5);
    uint32_t mm, ih, il;
    float rbest;
    uint32_t wf[128];
    const uint32_t frow = (ln & 7) + (ln >> 4) * 8;
    const uint32_t wfo = base + (warp & 1) * 8192 + frow * 64 + ((((ln >> 3) & 1) ^ ((frow >> 1) & 3)) << 4);
#define LOAD_WF(m) _Pragma("unroll") for (int f = 0; f < 16; f++) {                                                   \
      const int r = ((f >> 1) * 4 + (m) * 2 + (f & 1)) * 4;                                                           \
      ldmatrix4t(((wfo + unit_of((m) ? FT_U : FT_G, warp >> 1)) ^ ((f & 1) * 32)) + (f >> 1) * 1024, wf[r], wf[r + 1], wf[r + 2], wf[r + 3]); \
    }
    bool early, wait1;
    {
#pragma unroll
      for (int i = 0; i < 16; i += 2) stmatrix4((trow ^ ((i & 7) << 4)) + (i >> 3) * 16384, xr[2 * i], xr[2 * i + 1], xr[2 * i + 2], xr[2 * i + 3]);
      const uint4 cst = lds4(par + PAR_CONST);
      const float A1 = __uint_as_float(cst.x), A2 = __uint_as_float(cst.z);
      uint32_t n = 0;
      early = false; wait1 = false;
#pragma unroll 1
      while (true) {
        uint32_t miss;
        asm volatile("{ .reg .pred p0, p1, p2, p3; .reg .b64 u, v; .reg .b128 w;\n"
                     "setp.ge.u32 p0, %22, 2; setp.ne.and.u32 p0, %4, %21, p0; setp.ne.u32 p1, %8, %21; setp.ne.u32 p2, %12, %21; setp.ne.u32 p3, %16, %21;\n"
                     "@p0 ld.relaxed.gpu.global.v4.u32 {%1, %2, %3, %4}, [%17];\n"
                     "@p1 ld.relaxed.gpu.global.v4.u32 {%5, %6, %7, %8}, [%18];\n"
                     "@p2 ld.relaxed.gpu.global.v4.u32 {%9, %10, %11, %12}, [%19];\n"
                     "@p3 ld.relaxed.gpu.global.v4.u32 {%13, %14, %15, %16}, [%20];\n"
                     "or.pred p0, p0, p1; or.pred p2, p2, p3; or.pred p0, p0, p2; vote.sync.any.pred p0, p0, 0xffffffff; selp.u32 %0, 1, 0, p0; }"
                     : "=r"(miss), "+r"(sv[0].x), "+r"(sv[0].y), "+r"(sv[0].z), "+r"(sv[0].w), "+r"(sv[1].x), "+r"(sv[1].y), "+r"(sv[1].z), "+r"(sv[1].w),
                       "+r"(sv[2].x), "+r"(sv[2].y), "+r"(sv[2].z), "+r"(sv[2].w), "+r"(sv[3].x), "+r"(sv[3].y), "+r"(sv[3].z), "+r"(sv[3].w)
                     : "l"(sp[0]), "l"(sp[1]), "l"(sp[2]), "l"(sp[3]), "r"(tag), "r"(tq) : "memory");
        if (!miss) break;
        wait1 = true;
        if (!early && (b >= NFFN || __all_sync(0xffffffffu, mbar_test(bar_box + (warp >> 1) * 8, 0)))) {
          early = true;
          LOAD_WF(0);
          __syncwarp();
          mbar_arrive_pred(bar_gate, lane0);
        }
        watchdog(n);
      }
      const uint4 v0 = tq < 2 ? own : sv[0], v1 = sv[1], v2 = sv[2], v3 = sv[3];
      PROF(8, ct == PT, 30); STAMP(6);
      float su = (__uint_as_float(v0.x) + __uint_as_float(v1.x)) + (__uint_as_float(v2.x) + __uint_as_float(v3.x));
      float sq = (__uint_as_float(v0.y) + __uint_as_float(v1.y)) + (__uint_as_float(v2.y) + __uint_as_float(v3.y));
      float dt = (__uint_as_float(v0.z) + __uint_as_float(v1.z)) + (__uint_as_float(v2.z) + __uint_as_float(v3.z));
      su += __shfl_xor_sync(0xffffffffu, su, 2); sq += __shfl_xor_sync(0xffffffffu, sq, 2); dt += __shfl_xor_sync(0xffffffffu, dt, 2);
      const float m = su * (1.f / DM);
      float mb, sd;
      ln_scalars(m, fmaxf(sq * (1.f / DM) - m * m, 0.f), mb, sd);
      const float inv = rcp(sd);
      rbest = (dt - mb * A1) * inv + A2;
      mm = pack_bf(mb, mb);
      ih = pack_bf(inv, inv);
      const float lo = inv - bf_lo(ih);
      il = pack_bf(lo, lo);
    }
    int ibest;
    {
      const uint32_t bits = __float_as_uint(rbest);
      const uint32_t key = (((int)bits < 0 ? ~bits : bits | 0x80000000u) & ~0x1ffu) | ((127 - lrow0 - (tq & 1) * 8) << 2) | tag;
      sts1(par + PAR_RED + warp * 4, __reduce_max_sync(0xffffffffu, key));
      PROF(8, ct == PT, 38); STAMP(7);
      uint32_t waited;
      asm volatile("{ .reg .pred p, q; setp.ne.u32 p, %1, 0; barrier.cta.red.or.pred q, 1, 256, p; selp.u32 %0, 1, 0, q; }" : "=r"(waited) : "r"((uint32_t)(wait1 && (wg || CW0))) : "memory");
      const uint4 ka = lds4(par + PAR_RED), kb = lds4(par + PAR_RED + 16);
      const uint32_t k2 = max(max(max(ka.x, ka.y), max(ka.z, ka.w)), max(max(kb.x, kb.y), max(kb.z, kb.w)));
      if (ct == 0 && ((cj & CWM) == 0 || (CWL && !waited))) st_relaxed(g_cand + rb, k2);
      ibest = 127 - ((k2 >> 2) & 127);
    }
    PROF(8, ct == PT, 39); STAMP(8);
    if ((ibest >> 4) == warp) {
      const int src = (ibest & 7) * 4 + ((ibest >> 3) & 1), ch = g * 2;
      const uint32_t cm = __shfl_sync(0xffffffffu, mm, src), ch_ = __shfl_sync(0xffffffffu, ih, src), cl = __shfl_sync(0xffffffffu, il, src);
      const uint32_t xa = res + (ch >> 3) * 16384 + ibest * 128 + (((ch & 7) ^ (ibest & 7)) << 4) + tq * 4;
      const uint32_t x0 = lds1(xa), x1 = lds1(xa ^ 16);
      const uint2 p0 = lds2(par + PAR_T2 + ch * 64 + tq * 16), p1 = lds2(par + PAR_T2 + ch * 64 + 64 + tq * 16);
      uint32_t* dst = g_row + rb * 2 * DM + cj * 128 + ln * 4;
      st_pairs(dst, ln_mod(x0, cm, ch_, cl, p0.x, p0.y), ln_mod(x1, cm, ch_, cl, p1.x, p1.y), tag);
      st_pairs(dst + DM, x0, x1, tag);
      __syncwarp();
    }
    PROF(8, ct == PT, 37); STAMP(9);
    uint32_t wd[64];
    const uint32_t wda = base + unit_of(FT_D, warp >> 1) + (warp & 1) * 8192 + frow * 128 + ((((ln >> 3) & 1) ^ (ln & 7)) << 4);
#define LOAD_WD(f) ldmatrix4t((wda ^ ((((f) >> 1) & 3) * 32)) + ((f) >> 3) * 4096 + ((f) & 1) * 2048, wd[4 * (f)], wd[4 * (f) + 1], wd[4 * (f) + 2], wd[4 * (f) + 3])
    if (!early) {
      if (b < NFFN) mbar_wait(bar_box + (warp >> 1) * 8, 0);
      LOAD_WF(0);
      __syncwarp();
      mbar_arrive_pred(bar_gate, lane0);
    }
    if (b < NFFN) {
      const uint32_t own = base + unit_of(FT_G, warp >> 1) + (warp & 1) * 8192;
      mbar_wait(bar_box + (4 + (warp >> 1)) * 8, 0);
      LOAD_WF(1);
      uint32_t* const ydst = g_ypart + ((size_t)(warp * 16 + tq * 2) * NFFN + b) * 8 + g;
      PROF(8, ct == PT, 31); STAMP(10);
      mbar_wait(bar_box + (8 + (warp >> 1)) * 8, 0);
#pragma unroll
      for (int f = 0; f < WDE; f++) LOAD_WD(f);
      STAMP(11);
      mbar_wait(bar_sel, 0);
      PROF(8, ct == PT, 33); STAMP(12);
      float d[8][4];
#pragma unroll
      for (int i = 0; i < 4; i++) { d[i][0] = 0.f; d[i][1] = 0.f; d[i][2] = 0.f; d[i][3] = 0.f; }
#pragma unroll
      for (int ks = 0; ks < 8; ks++) {
        const uint2 hb = lds2(own + 256 + ks * 32 + tq * 8);
#pragma unroll
        for (int mt = 0; mt < 4; mt++) {
          const int r = ks * 16 + mt * 4;
          mma16816(d[mt], wf[r], wf[r + 1], wf[r + 2], wf[r + 3], hb.x, hb.y);
        }
      }
      sts2(own + (tq * 8 + g) * 8, __float_as_uint((tq & 2) ? ((tq & 1) ? d[1][2] : d[1][0]) : ((tq & 1) ? d[0][2] : d[0][0])),
           __float_as_uint((tq & 2) ? ((tq & 1) ? d[3][2] : d[3][0]) : ((tq & 1) ? d[2][2] : d[2][0])));
      bar_sync(1, 256);
      uint32_t ab[4];
      {
        float G = 0.f, U = 0.f;
        uint2 pv[8];
#pragma unroll
        for (int w8 = 0; w8 < 8; w8++) pv[w8] = lds2(base + ln * 8 + ((FT_G >> (w8 >> 1) * 4) & 15) * UNIT + (w8 & 1) * 8192);
#pragma unroll
        for (int w8 = 0; w8 < 8; w8 += 2) {
          G += __uint_as_float(pv[w8].x) + __uint_as_float(pv[w8 + 1].x);
          U += __uint_as_float(pv[w8].y) + __uint_as_float(pv[w8 + 1].y);
        }
#pragma unroll
        for (int f = WDE; f < 16; f++) LOAD_WD(f);
        const float act = rbf(silu_f(rbf(G))) * rbf(U);
        const uint32_t pk = pack_bf(act, __shfl_down_sync(0xffffffffu, act, 1));
#pragma unroll
        for (int i = 0; i < 4; i++) ab[i] = __shfl_sync(0xffffffffu, pk, i * 8 + tq * 2);
      }
      PROF(8, ct == PT, 34); STAMP(13);
#pragma unroll
      for (int mt = 0; mt < 8; mt++) {
        d[mt][0] = 0.f; d[mt][1] = 0.f; d[mt][2] = 0.f; d[mt][3] = 0.f;
        mma16816(d[mt], wd[mt * 8], wd[mt * 8 + 1], wd[mt * 8 + 2], wd[mt * 8 + 3], ab[0], ab[1]);
        mma16816(d[mt], wd[mt * 8 + 4], wd[mt * 8 + 5], wd[mt * 8 + 6], wd[mt * 8 + 7], ab[2], ab[3]);
      }
#pragma unroll
      for (int i = 0; i < 4; i++) {
        const int m4 = (i >> 1) * 4, e = (i & 1) * 2;
        const float y = (tq & 2) ? ((tq & 1) ? d[m4 + 3][e] : d[m4 + 2][e]) : ((tq & 1) ? d[m4 + 1][e] : d[m4][e]);
        st_relaxed(ydst + (m4 * 2 + (i & 1)) * NFFN * 8, tagf(y, tag));
      }
      PROF(8, ct == PT, 35); STAMP(14);
    }
    mbar_wait(bar_sel, 0);
    mbar_arrive_pred(bar_win, ct == 0);
    const int iwin = lds1(par + PAR_CONST + 60) & 0x7ff;
    {
      const uint32_t mm0 = __shfl_sync(0xffffffffu, mm, ln & ~1), mm1 = __shfl_sync(0xffffffffu, mm, ln | 1);
      const uint32_t ih0 = __shfl_sync(0xffffffffu, ih, ln & ~1), ih1 = __shfl_sync(0xffffffffu, ih, ln | 1);
      const uint32_t il0 = __shfl_sync(0xffffffffu, il, ln & ~1), il1 = __shfl_sync(0xffffffffu, il, ln | 1);
      const bool mine = (iwin >> 4) == rb * 8 + warp;
#pragma unroll 1
      for (int hf = 0; hf < 2; hf++) {
        uint32_t x[16];
#pragma unroll
        for (int i = 0; i < 8; i += 2) ldmatrix4((trow ^ (i << 4)) + hf * 16384, x[2 * i], x[2 * i + 1], x[2 * i + 2], x[2 * i + 3]);
#pragma unroll
        for (int i = 0; i < 8; i++) {
          const uint4 pv = lds4(par + PAR_T2 + (hf * 8 + i) * 64 + tq * 16);
          x[2 * i] = hadd2(x[2 * i], hmul2(pv.z, ln_mod(x[2 * i], mm0, ih0, il0, pv.x, pv.y)));
          x[2 * i + 1] = hadd2(x[2 * i + 1], hmul2(pv.z, ln_mod(x[2 * i + 1], mm1, ih1, il1, pv.x, pv.y)));
        }
        if (mine) {
          uint32_t* dst = reinterpret_cast<uint32_t*>(P.out + (size_t)grow0 * DM + cj * 128 + hf * 64) + tq;
#pragma unroll
          for (int i = 0; i < 8; i++) {
            if (grow0 != iwin) dst[i * 4] = x[2 * i];
            if (grow0 + 8 != iwin) dst[i * 4 + 4 * DM] = x[2 * i + 1];
          }
        } else {
#pragma unroll
          for (int i = 0; i < 8; i += 2) stmatrix4((trow ^ (i << 4)) + hf * 16384, x[2 * i], x[2 * i + 1], x[2 * i + 2], x[2 * i + 3]);
          fence_async_smem();
          __syncwarp();
          if (elect_one()) {
            tma2d_store(&maps.out, res + hf * 16384 + warp * 2048, cj * 128 + hf * 64, rb * 128 + warp * 16);
            asm volatile("cp.async.bulk.commit_group;" ::: "memory");
          }
        }
      }
      asm volatile("cp.async.bulk.wait_group.read 0;" ::: "memory");
    }
    PROF(8, ct == PT, 11); STAMP(15);
    cluster_wait();
  }
}

typedef CUresult (*EncodeFn)(CUtensorMap*, CUtensorMapDataType, cuuint32_t, void*, const cuuint64_t*, const cuuint64_t*,
                             const cuuint32_t*, const cuuint32_t*, CUtensorMapInterleave, CUtensorMapSwizzle,
                             CUtensorMapL2promotion, CUtensorMapFloatOOBfill);

void map2d(EncodeFn enc, CUtensorMap* m, const void* p, uint64_t rows, uint64_t cols, uint32_t brows) {
  cuuint64_t dims[2] = {cols, rows}, strides[1] = {cols * 2};
  cuuint32_t box[2] = {64, brows}, es[2] = {1, 1};
  enc(m, CU_TENSOR_MAP_DATA_TYPE_BFLOAT16, 2, const_cast<void*>(p), dims, strides, box, es, CU_TENSOR_MAP_INTERLEAVE_NONE,
      CU_TENSOR_MAP_SWIZZLE_128B, CU_TENSOR_MAP_L2_PROMOTION_L2_256B, CU_TENSOR_MAP_FLOAT_OOB_FILL_NONE);
}
void map2d_narrow(EncodeFn enc, CUtensorMap* m, const void* p, uint64_t rows, uint64_t cols, uint32_t brows) {
  cuuint64_t dims[2] = {cols, rows}, strides[1] = {cols * 2};
  cuuint32_t box[2] = {32, brows}, es[2] = {1, 1};
  enc(m, CU_TENSOR_MAP_DATA_TYPE_BFLOAT16, 2, const_cast<void*>(p), dims, strides, box, es, CU_TENSOR_MAP_INTERLEAVE_NONE,
      CU_TENSOR_MAP_SWIZZLE_64B, CU_TENSOR_MAP_L2_PROMOTION_L2_64B, CU_TENSOR_MAP_FLOAT_OOB_FILL_NONE);
}
void map3d(EncodeFn enc, CUtensorMap* m, const void* p, uint64_t rows, uint64_t cols, uint32_t brows, uint32_t nch) {
  cuuint64_t dims[3] = {64, rows, cols / 64}, strides[2] = {cols * 2, 128};
  cuuint32_t box[3] = {64, brows, nch}, es[3] = {1, 1, 1};
  enc(m, CU_TENSOR_MAP_DATA_TYPE_BFLOAT16, 3, const_cast<void*>(p), dims, strides, box, es, CU_TENSOR_MAP_INTERLEAVE_NONE,
      CU_TENSOR_MAP_SWIZZLE_128B, CU_TENSOR_MAP_L2_PROMOTION_L2_256B, CU_TENSOR_MAP_FLOAT_OOB_FILL_NONE);
}

}

extern "C" void kernel_launch(void* const* d_in, const int* in_sizes, int n_in, void* d_out, int out_size) {
  (void)in_sizes; (void)n_in; (void)out_size;
  static EncodeFn enc = nullptr;
  if (!enc) {
    void* fn = nullptr;
    cudaDriverEntryPointQueryResult st;
    cudaGetDriverEntryPoint("cuTensorMapEncodeTiled", &fn, cudaEnableDefault, &st);
    enc = (EncodeFn)fn;
    cudaFuncSetAttribute(fused_kernel, cudaFuncAttributeMaxDynamicSharedMemorySize, SMEM_BYTES);
  }
  Maps maps;
  map2d(enc, &maps.x, d_in[0], SEQ, DM, 128);
  map2d(enc, &maps.out, d_out, SEQ, DM, 16);
  map3d(enc, &maps.wq, d_in[3], DM, NQ, 64, 2);
  map3d(enc, &maps.k, d_in[1], 4 * SK, 128, 128, 1);
  map3d(enc, &maps.v, d_in[2], 4 * SK, 128, 128, 1);
  map3d(enc, &maps.wo, d_in[4], NQ, DM, 64, 2);
  map2d_narrow(enc, &maps.wg, d_in[7], DM, FF, 256);
  map2d_narrow(enc, &maps.wu, d_in[8], DM, FF, 256);
  map3d(enc, &maps.wd, d_in[9], FF, DM, 32, 4);
  map2d_narrow(enc, &maps.wm, d_in[11], DM, NMOD, 256);
  Ptrs p;
  p.x = (const __nv_bfloat16*)d_in[0];
  p.w_r = (const __nv_bfloat16*)d_in[6];
  p.w_gate = (const __nv_bfloat16*)d_in[7];
  p.w_up = (const __nv_bfloat16*)d_in[8];
  p.w_down = (const __nv_bfloat16*)d_in[9];
  p.c = (const __nv_bfloat16*)d_in[10];
  p.w_mod = (const __nv_bfloat16*)d_in[11];
  p.out = (__nv_bfloat16*)d_out;
  fused_kernel<<<NMAIN + NHELP, 384, SMEM_BYTES>>>(maps, p);
}
```

```cpp
#include <cuda_runtime.h>
#include <cuda_bf16.h>
#include <cuda.h>
#include <stdint.h>
#include <type_traits>

#define HD 1
#define HDX 2
#define XF 4
#define XE 32
#define XR 0
#define NRS 8
#define FPACE 3
#define GOST 20
#define WB 3
#define WN 24
#define RES0 17
#define RES1 20
#define HU 32
#define NS1 6
#define PG0 0
#define PSL 0
#define CWM 7
#define WDE 16
#define CWL 1
#define CW0 0
#define ESV 1
#define PPOS 1
#define FB0 0
#define FB2 8
#define OPS 8192
#define OFL 0
#define ODS 8
#define PORD 1
#define VREL 7
#define E0 3

namespace {

constexpr int SEQ = 2048, DM = 1024, NQ = 4096, SK = 2048, WIN = 512, FF = 3584, NMOD = 6144;
constexpr int NMAIN = 128, NHELP = 4, NFFN = 112;
constexpr int NSLOT = 4, SLOT_BYTES = 32768, UNIT = 16384, GST_BYTES = 3 * UNIT;
constexpr uint32_t XT1 = 0xDCBA, XT2 = 0x9687;
constexpr uint32_t WT0 = 0xA741, WT1 = 0x7420, WT2 = 0x4A20;
constexpr uint32_t AT0 = WT1, AT1 = WT2;
constexpr uint32_t QT = 0xDC9696DC;
constexpr int OFF_STAGE = 12 * UNIT;
constexpr uint32_t FT_G = 0x07B3, FT_U = 0xA628, FT_D = 0x5149;
constexpr int OFF_RES = 12 * UNIT;
constexpr int OFF_PAR = 14 * UNIT;
constexpr int OFF_BAR = OFF_PAR + 2528;
constexpr int SMEM_BYTES = OFF_BAR + 544;
static_assert(SMEM_BYTES <= 232448, "smem");

constexpr int PAR_T1 = 0;
constexpr int PAR_T2 = 512;
constexpr int PAR_CONST = 1536;
constexpr int PAR_RED = 1600;
constexpr int PAR_SINK = 2176;

struct Maps {
  CUtensorMap x, wq, k, v, wo, wg, wu, wd, wm, out;
};
struct Ptrs {
  const __nv_bfloat16 *x, *w_r, *c, *w_mod, *w_gate, *w_up, *w_down;
  __nv_bfloat16* out;
};

__device__ __align__(1024) uint8_t g_act[16 * 80 * UNIT];
__device__ __align__(128) uint32_t g_mod[NMOD];
__device__ __align__(128) uint32_t g_modp[2 * 2 * DM];
__device__ __align__(128) uint32_t g_ln1[SEQ * 4];
__device__ __align__(128) uint32_t g_cnt_h[16 * 32];
__device__ __align__(128) uint32_t g_cnt_o[128 * 32];
__device__ __align__(128) uint32_t g_xch[NMAIN * 8 * 256 * 4];
__device__ __align__(128) uint32_t g_stats[8 * SEQ * 4];
__device__ __align__(128) uint32_t g_cand[32];
__device__ __align__(128) uint32_t g_row[16 * 2 * DM];
__device__ __align__(128) uint32_t g_ypart[NMAIN * NFFN * 8];
__device__ uint32_t g_epoch;

__device__ __forceinline__ uint32_t fresh_lane() { uint32_t l; asm volatile("mov.u32 %0, %%laneid;" : "=r"(l)); return l; }
__device__ __forceinline__ uint32_t frag_offset(int warp) {
  const uint32_t l = fresh_lane();
  return ((warp & 3) * 16 + (l & 15)) * 128 + (((l >> 4) ^ (l & 7)) << 4);
}
__device__ __forceinline__ bool elect_one() {
  uint32_t p;
  asm volatile("{ .reg .pred q; elect.sync _|q, 0xffffffff; selp.u32 %0, 1, 0, q; }" : "=r"(p));
  return p;
}
__device__ __forceinline__ uint32_t smem_u32(const void* p) { return (uint32_t)__cvta_generic_to_shared(p); }
__device__ __forceinline__ void mbar_init(uint32_t bar, uint32_t cnt) {
  asm volatile("mbarrier.init.shared::cta.b64 [%0], %1;" ::"r"(bar), "r"(cnt) : "memory");
}
__device__ __forceinline__ void mbar_expect_tx(uint32_t bar, uint32_t bytes) {
  asm volatile("mbarrier.arrive.expect_tx.shared::cta.b64 _, [%0], %1;" ::"r"(bar), "r"(bytes) : "memory");
}
__device__ __forceinline__ void mbar_arrive(uint32_t bar) {
  asm volatile("mbarrier.arrive.shared::cta.b64 _, [%0];" ::"r"(bar) : "memory");
}
__device__ __forceinline__ void mbar_arrive_pred(uint32_t bar, bool p) {
  asm volatile("{ .reg .pred p; setp.ne.b32 p, %1, 0; @p mbarrier.arrive.shared::cta.b64 _, [%0]; }" ::"r"(bar), "r"((int)p) : "memory");
}
__device__ __forceinline__ void mbar_arrive_cl(uint32_t bar, uint32_t off, bool p = true) {
  asm volatile("{ .reg .pred p, q; .reg .b32 a; setp.ne.b32 q, %2, 0; setp.ne.and.b32 p, %0, 0, q; add.u32 a, %0, %1; @p mbarrier.arrive.shared::cluster.b64 _, [a]; }"
               ::"r"(bar), "r"(off), "r"((int)p) : "memory");
}
__device__ __forceinline__ uint32_t mapa(uint32_t addr, uint32_t cta) {
  uint32_t r; asm("mapa.shared::cluster.u32 %0, %1, %2;" : "=r"(r) : "r"(addr), "r"(cta)); return r;
}
__device__ __forceinline__ void cluster_arrive() { asm volatile("barrier.cluster.arrive.relaxed.aligned;" ::: "memory"); }
__device__ __forceinline__ void cluster_wait() { asm volatile("barrier.cluster.wait.aligned;" ::: "memory"); }
__device__ __forceinline__ void watchdog(uint32_t& n) {
}
__device__ __forceinline__ void mbar_wait(uint32_t bar, uint32_t parity) {
  asm volatile("{\n.reg .pred p;\nWAIT_%=:\nmbarrier.try_wait.parity.shared::cta.b64 p, [%0], %1;\n@!p bra WAIT_%=;\n}" ::"r"(bar), "r"(parity) : "memory");
}
__device__ __forceinline__ bool mbar_test(uint32_t bar, uint32_t parity) {
  uint32_t ok;
  asm volatile("{\n.reg .pred p;\nmbarrier.test_wait.parity.shared::cta.b64 p, [%1], %2;\nselp.u32 %0, 1, 0, p;\n}" : "=r"(ok) : "r"(bar), "r"(parity) : "memory");
  return ok;
}
__device__ __forceinline__ uint64_t l2_stream() {
  uint64_t f; asm("createpolicy.fractional.L2::evict_first.b64 %0, 1.0;" : "=l"(f)); return f;
}
__device__ __forceinline__ void tma2d(uint32_t dst, const CUtensorMap* m, int c0, int c1, uint32_t bar) {
  asm volatile("cp.async.bulk.tensor.2d.shared::cluster.global.mbarrier::complete_tx::bytes.L2::cache_hint [%0], [%1, {%3, %4}], [%2], %5;"
               ::"r"(dst), "l"(m), "r"(bar), "r"(c0), "r"(c1), "l"(l2_stream()) : "memory");
}
__device__ __forceinline__ void bulk_load(uint32_t dst, const void* src, uint32_t bytes, uint32_t bar) {
  asm volatile("cp.async.bulk.shared::cluster.global.mbarrier::complete_tx::bytes [%0], [%1], %2, [%3];" ::"r"(dst), "l"(src), "r"(bytes), "r"(bar) : "memory");
}
__device__ __forceinline__ void bulk_load_stream(uint32_t dst, const void* src, uint32_t bytes, uint32_t bar) {
  asm volatile("cp.async.bulk.shared::cluster.global.mbarrier::complete_tx::bytes.L2::cache_hint [%0], [%1], %2, [%3], %4;"
               ::"r"(dst), "l"(src), "r"(bytes), "r"(bar), "l"(l2_stream()) : "memory");
}
__device__ __forceinline__ void tma2d_store(const CUtensorMap* m, uint32_t src, int c0, int c1) {
  asm volatile("cp.async.bulk.tensor.2d.global.shared::cta.bulk_group [%0, {%2, %3}], [%1];" ::"l"(m), "r"(src), "r"(c0), "r"(c1) : "memory");
}
__device__ __forceinline__ void bulk_store(void* dst, uint32_t src, uint32_t bytes) {
  asm volatile("cp.async.bulk.global.shared::cta.bulk_group [%0], [%1], %2;" ::"l"(dst), "r"(src), "r"(bytes) : "memory");
}
__device__ __forceinline__ uint32_t unit_of(uint32_t table, uint32_t i) { return ((table >> (i * 4)) & 15) * UNIT; }
__device__ __forceinline__ void tma3d(uint32_t dst, const CUtensorMap* m, int c0, int c1, int c2, uint32_t bar) {
  asm volatile("cp.async.bulk.tensor.3d.shared::cluster.global.mbarrier::complete_tx::bytes.L2::cache_hint [%0], [%1, {%3, %4, %5}], [%2], %6;"
               ::"r"(dst), "l"(m), "r"(bar), "r"(c0), "r"(c1), "r"(c2), "l"(l2_stream()) : "memory");
}
template <bool STREAM>
__device__ __forceinline__ void tma3d_mc(uint32_t dst, const CUtensorMap* m, int c0, int c1, int c2, uint32_t bar) {
  if (STREAM)
    asm volatile("cp.async.bulk.tensor.3d.shared::cluster.global.mbarrier::complete_tx::bytes.multicast::cluster.L2::cache_hint [%0], [%1, {%3, %4, %5}], [%2], %6, %7;"
                 ::"r"(dst), "l"(m), "r"(bar), "r"(c0), "r"(c1), "r"(c2), "h"((uint16_t)3), "l"(l2_stream()) : "memory");
  else
    asm volatile("cp.async.bulk.tensor.3d.shared::cluster.global.mbarrier::complete_tx::bytes.multicast::cluster [%0], [%1, {%3, %4, %5}], [%2], %6;"
                 ::"r"(dst), "l"(m), "r"(bar), "r"(c0), "r"(c1), "r"(c2), "h"((uint16_t)3) : "memory");
}
__device__ __forceinline__ void prefetch_map(const CUtensorMap* m) {
  asm volatile("prefetch.tensormap [%0];" ::"l"(m) : "memory");
}
__device__ __forceinline__ void fence_async() { asm volatile("fence.proxy.async.global;" ::: "memory"); }
__device__ __forceinline__ void fence_async_smem() { asm volatile("fence.proxy.async.shared::cta;" ::: "memory"); }
__device__ __forceinline__ void bar_sync(int id, int n) { asm volatile("bar.sync %0, %1;" ::"r"(id), "r"(n) : "memory"); }
__device__ __forceinline__ void bar_arrive(int id, int n) { asm volatile("bar.arrive %0, %1;" ::"r"(id), "r"(n) : "memory"); }
__device__ __forceinline__ void wg_fence() { asm volatile("wgmma.fence.sync.aligned;" ::: "memory"); }
__device__ __forceinline__ void wg_commit() { asm volatile("wgmma.commit_group.sync.aligned;" ::: "memory"); }
template <int N> __device__ __forceinline__ void wg_wait() { asm volatile("wgmma.wait_group.sync.aligned %0;" ::"n"(N) : "memory"); }
__device__ __forceinline__ uint64_t make_desc(uint32_t addr, uint32_t lbo, uint32_t sbo) {
  return (uint64_t)((addr & 0x3FFFF) >> 4) | ((uint64_t)(lbo >> 4) << 16) | ((uint64_t)(sbo >> 4) << 32) | (1ull << 62);
}
__device__ __forceinline__ uint32_t ld_relaxed(const uint32_t* p) {
  uint32_t v; asm volatile("ld.relaxed.gpu.global.u32 %0, [%1];" : "=r"(v) : "l"(p) : "memory"); return v;
}
__device__ __forceinline__ uint32_t ld_acquire(const uint32_t* p) {
  uint32_t v; asm volatile("ld.acquire.gpu.global.u32 %0, [%1];" : "=r"(v) : "l"(p) : "memory"); return v;
}
__device__ __forceinline__ uint4 ld_relaxed4(const uint32_t* p) {
  uint4 v; asm volatile("ld.relaxed.gpu.global.v4.u32 {%0,%1,%2,%3}, [%4];" : "=r"(v.x), "=r"(v.y), "=r"(v.z), "=r"(v.w) : "l"(p) : "memory"); return v;
}
__device__ __forceinline__ uint2 ld_relaxed2(const uint32_t* p) {
  uint2 v; asm volatile("ld.relaxed.gpu.global.v2.u32 {%0,%1}, [%2];" : "=r"(v.x), "=r"(v.y) : "l"(p) : "memory"); return v;
}
__device__ __forceinline__ void st_relaxed(uint32_t* p, uint32_t v) {
  asm volatile("st.relaxed.gpu.global.u32 [%0], %1;" ::"l"(p), "r"(v) : "memory");
}
__device__ __forceinline__ void st_relaxed2(uint32_t* p, uint32_t a, uint32_t b) {
  asm volatile("st.relaxed.gpu.global.v2.u32 [%0], {%1,%2};" ::"l"(p), "r"(a), "r"(b) : "memory");
}
__device__ __forceinline__ void st_relaxed4(uint32_t* p, uint32_t a, uint32_t b, uint32_t c, uint32_t d) {
  asm volatile("st.relaxed.gpu.global.v4.u32 [%0], {%1,%2,%3,%4};" ::"l"(p), "r"(a), "r"(b), "r"(c), "r"(d) : "memory");
}
__device__ __forceinline__ void st_b128(uint32_t* p, uint32_t a, uint32_t b, uint32_t c, uint32_t d) {
  asm volatile("{ .reg .b64 u, v; .reg .b128 w; mov.b64 u, {%1, %2}; mov.b64 v, {%3, %4}; mov.b128 w, {u, v}; st.relaxed.gpu.global.b128 [%0], w; }"
               ::"l"(p), "r"(a), "r"(b), "r"(c), "r"(d) : "memory");
}
__device__ __forceinline__ uint4 ld_b128(const uint32_t* p) {
  uint4 r;
  asm volatile("{ .reg .b64 u, v; .reg .b128 w; ld.relaxed.gpu.global.b128 w, [%4]; mov.b128 {u, v}, w; mov.b64 {%0, %1}, u; mov.b64 {%2, %3}, v; }"
               : "=r"(r.x), "=r"(r.y), "=r"(r.z), "=r"(r.w) : "l"(p) : "memory");
  return r;
}
__device__ __forceinline__ void st_pairs(uint32_t* p, uint32_t a, uint32_t b, uint32_t tag) {
  asm volatile("{ .reg .b64 u, v; mov.b64 u, {%1, %3}; mov.b64 v, {%2, %3}; st.relaxed.gpu.global.v2.b64 [%0], {u, v}; }"
               ::"l"(p), "r"(a), "r"(b), "r"(tag) : "memory");
}
__device__ __forceinline__ uint4 ld_pairs(const uint32_t* p) {
  uint4 v;
  asm volatile("{ .reg .b64 u, v; ld.relaxed.gpu.global.v2.b64 {u, v}, [%4]; mov.b64 {%0, %1}, u; mov.b64 {%2, %3}, v; }"
               : "=r"(v.x), "=r"(v.y), "=r"(v.z), "=r"(v.w) : "l"(p) : "memory");
  return v;
}
__device__ __forceinline__ uint2 ld_pair(const uint32_t* p) {
  uint2 v;
  asm volatile("{ .reg .b64 u; ld.relaxed.gpu.global.b64 u, [%2]; mov.b64 {%0, %1}, u; }" : "=r"(v.x), "=r"(v.y) : "l"(p) : "memory");
  return v;
}
__device__ __forceinline__ void red_release(uint32_t* p, uint32_t v) {
  asm volatile("red.release.gpu.global.add.u32 [%0], %1;" ::"l"(p), "r"(v) : "memory");
}
__device__ __forceinline__ uint32_t ldg_nc1(const void* p) {
  uint32_t v;
  asm volatile("ld.global.nc.u32 %0, [%1];" : "=r"(v) : "l"(p));
  return v;
}
__device__ __forceinline__ uint4 ldg_nc4(const void* p) {
  uint4 v; asm volatile("ld.global.nc.L1::no_allocate.v4.u32 {%0,%1,%2,%3}, [%4];" : "=r"(v.x), "=r"(v.y), "=r"(v.z), "=r"(v.w) : "l"(p)); return v;
}
__device__ __forceinline__ uint4 ldg_stream4(const void* p) {
  uint4 v;
  asm volatile("ld.global.nc.L1::no_allocate.L2::cache_hint.v4.u32 {%0,%1,%2,%3}, [%4], %5;" : "=r"(v.x), "=r"(v.y), "=r"(v.z), "=r"(v.w) : "l"(p), "l"(l2_stream()));
  return v;
}
__device__ __forceinline__ void stg4(void* p, uint4 v) {
  asm volatile("st.global.v4.u32 [%0], {%1,%2,%3,%4};" ::"l"(p), "r"(v.x), "r"(v.y), "r"(v.z), "r"(v.w) : "memory");
}
__device__ __forceinline__ void wait_counter(const uint32_t* p, uint32_t target) {
  uint32_t n = 0;
  while ((int)(ld_acquire(p) - target) < 0) { watchdog(n); }
}
__device__ __forceinline__ uint32_t tagf(float v, uint32_t tag) { return (__float_as_uint(v) & ~3u) | tag; }
__device__ __forceinline__ bool tag_ok(uint4 v, uint32_t tag) { return (((v.x ^ tag) | (v.y ^ tag) | (v.z ^ tag) | (v.w ^ tag)) & 3u) == 0; }
__device__ __forceinline__ float untag_sum(uint32_t a, uint32_t b) { return __uint_as_float(a & ~3u) + __uint_as_float(b & ~3u); }
__device__ __forceinline__ uint4 poll4(const uint32_t* p, uint32_t tag) {
  uint4 v = ld_relaxed4(p);
  uint32_t n = 0;
  while (!tag_ok(v, tag)) { v = ld_relaxed4(p); watchdog(n); }
  return v;
}
__device__ __forceinline__ float bf_lo(uint32_t v) { return __uint_as_float(v << 16); }
__device__ __forceinline__ float bf_hi(uint32_t v) { return __uint_as_float(v & 0xffff0000u); }
__device__ __forceinline__ uint32_t pack_bf(float lo, float hi) {
  uint32_t r; asm("cvt.rn.bf16x2.f32 %0, %1, %2;" : "=r"(r) : "f"(hi), "f"(lo)); return r;
}
__device__ __forceinline__ float rbf(float v) { return __uint_as_float(pack_bf(0.f, v) & 0xffff0000u); }
__device__ __forceinline__ uint32_t hmul2(uint32_t a, uint32_t b) {
  uint32_t r; asm("mul.rn.bf16x2 %0, %1, %2;" : "=r"(r) : "r"(a), "r"(b)); return r;
}
__device__ __forceinline__ uint32_t hadd2(uint32_t a, uint32_t b) {
  uint32_t r; asm("add.rn.bf16x2 %0, %1, %2;" : "=r"(r) : "r"(a), "r"(b)); return r;
}
__device__ __forceinline__ uint32_t hsub2(uint32_t a, uint32_t b) {
  uint32_t r; asm("sub.rn.bf16x2 %0, %1, %2;" : "=r"(r) : "r"(a), "r"(b)); return r;
}
__device__ __forceinline__ uint32_t hmax2(uint32_t a, uint32_t b) {
  uint32_t r; asm("max.bf16x2 %0, %1, %2;" : "=r"(r) : "r"(a), "r"(b)); return r;
}
__device__ __forceinline__ float rcp(float x) { float r; asm("rcp.approx.ftz.f32 %0, %1;" : "=f"(r) : "f"(x)); return r; }
__device__ __forceinline__ float ex2(float x) { float r; asm("ex2.approx.ftz.f32 %0, %1;" : "=f"(r) : "f"(x)); return r; }
__device__ __forceinline__ void stmatrix4(uint32_t addr, uint32_t a, uint32_t b, uint32_t c, uint32_t d) {
  asm volatile("stmatrix.sync.aligned.m8n8.x4.shared.b16 [%0], {%1,%2,%3,%4};" ::"r"(addr), "r"(a), "r"(b), "r"(c), "r"(d) : "memory");
}
__device__ __forceinline__ void ldmatrix4(uint32_t addr, uint32_t& a, uint32_t& b, uint32_t& c, uint32_t& d) {
  asm volatile("ldmatrix.sync.aligned.m8n8.x4.shared.b16 {%0,%1,%2,%3}, [%4];" : "=r"(a), "=r"(b), "=r"(c), "=r"(d) : "r"(addr) : "memory");
}
__device__ __forceinline__ void ldmatrix4t(uint32_t addr, uint32_t& a, uint32_t& b, uint32_t& c, uint32_t& d) {
  asm volatile("ldmatrix.sync.aligned.m8n8.x4.trans.shared.b16 {%0,%1,%2,%3}, [%4];" : "=r"(a), "=r"(b), "=r"(c), "=r"(d) : "r"(addr) : "memory");
}
__device__ __forceinline__ void mma16816(float (&d)[4], uint32_t a0, uint32_t a1, uint32_t a2, uint32_t a3, uint32_t b0, uint32_t b1) {
  asm volatile("mma.sync.aligned.m16n8k16.row.col.f32.bf16.bf16.f32 {%0,%1,%2,%3}, {%4,%5,%6,%7}, {%8,%9}, {%0,%1,%2,%3};"
               : "+f"(d[0]), "+f"(d[1]), "+f"(d[2]), "+f"(d[3]) : "r"(a0), "r"(a1), "r"(a2), "r"(a3), "r"(b0), "r"(b1));
}
__device__ __forceinline__ void sts1(uint32_t a, uint32_t v) { asm volatile("st.shared.u32 [%0], %1;" ::"r"(a), "r"(v) : "memory"); }
__device__ __forceinline__ uint4 lds4(uint32_t a) {
  uint4 v; asm volatile("ld.shared.v4.u32 {%0,%1,%2,%3}, [%4];" : "=r"(v.x), "=r"(v.y), "=r"(v.z), "=r"(v.w) : "r"(a) : "memory"); return v;
}
__device__ __forceinline__ uint2 lds2(uint32_t a) {
  uint2 v; asm volatile("ld.shared.v2.u32 {%0,%1}, [%2];" : "=r"(v.x), "=r"(v.y) : "r"(a) : "memory"); return v;
}
__device__ __forceinline__ uint32_t lds1(uint32_t a) {
  uint32_t v; asm volatile("ld.shared.u32 %0, [%1];" : "=r"(v) : "r"(a) : "memory"); return v;
}
__device__ __forceinline__ void sts2(uint32_t a, uint32_t x, uint32_t y) { asm volatile("st.shared.v2.u32 [%0], {%1,%2};" ::"r"(a), "r"(x), "r"(y) : "memory"); }
__device__ __forceinline__ void sts4(uint32_t a, uint4 v) {
  asm volatile("st.shared.v4.u32 [%0], {%1,%2,%3,%4};" ::"r"(a), "r"(v.x), "r"(v.y), "r"(v.z), "r"(v.w) : "memory");
}
__device__ __forceinline__ float silu_f(float v) { return __fdividef(v, 1.f + __expf(-v)); }
__device__ __forceinline__ uint32_t hfma2(uint32_t a, uint32_t b, uint32_t c) {
  uint32_t r; asm("fma.rn.bf16x2 %0, %1, %2, %3;" : "=r"(r) : "r"(a), "r"(b), "r"(c)); return r;
}
__device__ __forceinline__ void split_inv(float sd, uint32_t& ih, uint32_t& il) {
  const float inv = rcp(sd);
  ih = pack_bf(inv, inv);
  const float lo = inv - bf_lo(ih);
  il = pack_bf(lo, lo);
}
__device__ __forceinline__ uint32_t ln_norm(uint32_t x, uint32_t mean2, uint32_t ih, uint32_t il) {
  const uint32_t d = hsub2(x, mean2);
  return hfma2(d, ih, hmul2(d, il));
}
__device__ __forceinline__ uint32_t modul(uint32_t n, uint32_t c1, uint32_t sh) { return hadd2(hmul2(n, c1), sh); }
__device__ __forceinline__ uint32_t ln_mod(uint32_t x, uint32_t mean2, uint32_t ih, uint32_t il, uint32_t c1, uint32_t sh) {
  return modul(ln_norm(x, mean2, ih, il), c1, sh);
}

#define R8(a, i) "+f"(a[i]), "+f"(a[i + 1]), "+f"(a[i + 2]), "+f"(a[i + 3]), "+f"(a[i + 4]), "+f"(a[i + 5]), "+f"(a[i + 6]), "+f"(a[i + 7])
#define D64 "{%0,%1,%2,%3,%4,%5,%6,%7,%8,%9,%10,%11,%12,%13,%14,%15,%16,%17,%18,%19,%20,%21,%22,%23,%24,%25,%26,%27,%28,%29,%30,%31," \
            "%32,%33,%34,%35,%36,%37,%38,%39,%40,%41,%42,%43,%44,%45,%46,%47,%48,%49,%50,%51,%52,%53,%54,%55,%56,%57,%58,%59,%60,%61,%62,%63}"
template <int TB>
__device__ __forceinline__ void mma_ss(float (&d)[64], uint64_t da, uint64_t db, int sc) {
  asm volatile("{\n.reg .pred p;\nsetp.ne.b32 p, %66, 0;\n"
               "wgmma.mma_async.sync.aligned.m64n128k16.f32.bf16.bf16 " D64 ", %64, %65, p, 1, 1, 0, %67;\n}"
               : R8(d, 0), R8(d, 8), R8(d, 16), R8(d, 24), R8(d, 32), R8(d, 40), R8(d, 48), R8(d, 56)
               : "l"(da), "l"(db), "r"(sc), "n"(TB));
}
template <int TB>
__device__ __forceinline__ void mma_rs(float (&d)[64], uint32_t a0, uint32_t a1, uint32_t a2, uint32_t a3, uint64_t db, int sc) {
  asm volatile("{\n.reg .pred p;\nsetp.ne.b32 p, %69, 0;\n"
               "wgmma.mma_async.sync.aligned.m64n128k16.f32.bf16.bf16 " D64 ", {%64,%65,%66,%67}, %68, p, 1, 1, %70;\n}"
               : R8(d, 0), R8(d, 8), R8(d, 16), R8(d, 24), R8(d, 32), R8(d, 40), R8(d, 48), R8(d, 56)
               : "r"(a0), "r"(a1), "r"(a2), "r"(a3), "l"(db), "r"(sc), "n"(TB));
}
#define D128 "{%0,%1,%2,%3,%4,%5,%6,%7,%8,%9,%10,%11,%12,%13,%14,%15,%16,%17,%18,%19,%20,%21,%22,%23,%24,%25,%26,%27,%28,%29,%30,%31," \
             "%32,%33,%34,%35,%36,%37,%38,%39,%40,%41,%42,%43,%44,%45,%46,%47,%48,%49,%50,%51,%52,%53,%54,%55,%56,%57,%58,%59,%60,%61,%62,%63," \
             "%64,%65,%66,%67,%68,%69,%70,%71,%72,%73,%74,%75,%76,%77,%78,%79,%80,%81,%82,%83,%84,%85,%86,%87,%88,%89,%90,%91,%92,%93,%94,%95," \
             "%96,%97,%98,%99,%100,%101,%102,%103,%104,%105,%106,%107,%108,%109,%110,%111,%112,%113,%114,%115,%116,%117,%118,%119,%120,%121,%122,%123,%124,%125,%126,%127}"
#define R128(d, e) R8(d, 0), R8(d, 8), R8(d, 16), R8(d, 24), R8(d, 32), R8(d, 40), R8(d, 48), R8(d, 56), \
                   R8(e, 0), R8(e, 8), R8(e, 16), R8(e, 24), R8(e, 32), R8(e, 40), R8(e, 48), R8(e, 56)
__device__ __forceinline__ void mma256_ss(float (&d)[64], float (&e)[64], uint64_t da, uint64_t db, int sc) {
  asm volatile("{\n.reg .pred p;\nsetp.ne.b32 p, %130, 0;\n"
               "wgmma.mma_async.sync.aligned.m64n256k16.f32.bf16.bf16 " D128 ", %128, %129, p, 1, 1, 0, 1;\n}"
               : R128(d, e) : "l"(da), "l"(db), "r"(sc));
}
__device__ __forceinline__ void mma256_rs(float (&d)[64], float (&e)[64], uint32_t a0, uint32_t a1, uint32_t a2, uint32_t a3, uint64_t db) {
  asm volatile("{\n.reg .pred p;\nsetp.ne.b32 p, 1, 0;\n"
               "wgmma.mma_async.sync.aligned.m64n256k16.f32.bf16.bf16 " D128 ", {%128,%129,%130,%131}, %132, p, 1, 1, 1;\n}"
               : R128(d, e) : "r"(a0), "r"(a1), "r"(a2), "r"(a3), "l"(db));
}
template <int N> __device__ __forceinline__ void keep(float (&a)[N]) {
#pragma unroll
  for (int i = 0; i < N; i++) asm volatile("" : "+f"(a[i])::"memory");
}
template <int N> __device__ __forceinline__ void keep(uint32_t (&a)[N]) {
#pragma unroll
  for (int i = 0; i < N; i++) asm volatile("" : "+r"(a[i])::"memory");
}

#define STAMP(idx) do {} while (0)
#define PROF(grp, cond, idx) do {} while (0)

constexpr float SCL2 = 1.4426950408889634f * 0.08838834764831845f;

__device__ __forceinline__ void pack_p(const float (&s)[64], uint32_t (&p)[32]) {
#pragma unroll
  for (int i = 0; i < 32; i++) p[i] = pack_bf(s[2 * i], s[2 * i + 1]);
}

__device__ __forceinline__ void issue_qk(float (&s)[64], uint32_t q0, uint32_t q1, uint32_t kslot) {
  const uint64_t db = make_desc(kslot, 16, 1024), da0 = make_desc(q0, 16, 1024), da1 = make_desc(q1, 16, 1024);
#pragma unroll
  for (int kk = 0; kk < 8; kk++) mma_ss<0>(s, (kk < 4 ? da0 : da1) + (kk & 3) * 2, db + (kk >> 2) * 1024 + (kk & 3) * 2, kk != 0);
}
__device__ __forceinline__ void issue_pv(float (&o)[64], uint32_t (&p)[32], uint32_t vslot, int acc) {
  uint64_t db = make_desc(vslot, 16384, 1024);
#pragma unroll
  for (int kk = 0; kk < 8; kk++)
    mma_rs<1>(o, p[4 * kk], p[4 * kk + 1], p[4 * kk + 2], p[4 * kk + 3], db + kk * 128, kk == 0 ? acc : 1);
}

template <int H>
__device__ __forceinline__ void store_chunk(const float (&a)[64], uint32_t addr) {
#pragma unroll
  for (int i = 8 * H; i < 8 * H + 8; i += 2)
    stmatrix4(addr ^ ((i & 7) << 4), pack_bf(a[4 * i], a[4 * i + 1]), pack_bf(a[4 * i + 2], a[4 * i + 3]),
              pack_bf(a[4 * i + 4], a[4 * i + 5]), pack_bf(a[4 * i + 6], a[4 * i + 7]));
}
template <int H>
__device__ __forceinline__ void store_chunk(const float (&a)[64], float i0, float i1, uint32_t addr) {
#pragma unroll
  for (int i = 8 * H; i < 8 * H + 8; i += 2)
    stmatrix4(addr ^ ((i & 7) << 4), pack_bf(a[4 * i] * i0, a[4 * i + 1] * i0), pack_bf(a[4 * i + 2] * i1, a[4 * i + 3] * i1),
              pack_bf(a[4 * i + 4] * i0, a[4 * i + 5] * i0), pack_bf(a[4 * i + 6] * i1, a[4 * i + 7] * i1));
}
__device__ __forceinline__ float inv_quad_sum(float l) {
  l += __shfl_xor_sync(0xffffffffu, l, 1);
  l += __shfl_xor_sync(0xffffffffu, l, 2);
  return rcp(l);
}

__device__ __forceinline__ void ln_scalars(float mean, float var, float& mb, float& sd) {
  mb = rbf(mean);
  float r; asm("sqrt.approx.ftz.f32 %0, %1;" : "=f"(r) : "f"(rbf(rbf(var) + 1e-5f)));
  sd = rbf(r);
}

__global__ void __cluster_dims__(2, 1, 1) __launch_bounds__(384, 1) fused_kernel(const __grid_constant__ Maps maps, const Ptrs P) {
  extern __shared__ __align__(1024) uint8_t smem_raw[];
  const uint32_t base = smem_u32(smem_raw);
  const int tid = threadIdx.x, lane = tid & 31;
  const int warp = __shfl_sync(0xffffffffu, tid >> 5, 0);
  const int b = blockIdx.x;
  PROF(31, tid == 0, 0);

  if (b >= NMAIN) {
    float* sc = reinterpret_cast<float*>(smem_raw);
    float* red = sc + DM;
    for (int k = tid; k < DM; k += 384) sc[k] = rbf(silu_f(__bfloat162float(P.c[k])));
    __syncthreads();
    if (tid < 256) {
      const int col = 2048 + (b - NMAIN) * 1024 + (tid & 127) * 8, r0 = (tid >> 7) * 512;
      float acc[8];
#pragma unroll
      for (int e = 0; e < 8; e++) acc[e] = 0.f;
#pragma unroll 1
      for (int r = r0; r < r0 + 512; r += HU) {
        uint4 w[HU];
#pragma unroll
        for (int u = 0; u < HU; u++) w[u] = ldg_stream4(P.w_mod + (size_t)(r + u) * NMOD + col);
#pragma unroll
        for (int u = 0; u < HU; u++) {
          float s = sc[r + u];
          acc[0] += s * bf_lo(w[u].x); acc[1] += s * bf_hi(w[u].x); acc[2] += s * bf_lo(w[u].y); acc[3] += s * bf_hi(w[u].y);
          acc[4] += s * bf_lo(w[u].z); acc[5] += s * bf_hi(w[u].z); acc[6] += s * bf_lo(w[u].w); acc[7] += s * bf_hi(w[u].w);
        }
      }
      if (tid >= 128) {
#pragma unroll
        for (int e = 0; e < 8; e++) red[(tid & 127) * 8 + e] = acc[e];
      }
      const uint32_t tag = ld_relaxed(&g_epoch) % 3 + 1;
      bar_sync(1, 256);
      if (tid < 128) {
        uint32_t o[8];
#pragma unroll
        for (int e = 0; e < 8; e++) o[e] = __float_as_uint(rbf(acc[e] + red[tid * 8 + e])) | tag;
        st_relaxed4(g_mod + col, o[0], o[1], o[2], o[3]);
        st_relaxed4(g_mod + col + 4, o[4], o[5], o[6], o[7]);
        const uint4 wr = ldg_nc4(P.w_r + tid * 8);
        const uint32_t wv[4] = {wr.x, wr.y, wr.z, wr.w};
        float dsum = 0.f;
#pragma unroll
        for (int e = 0; e < 8; e++) {
          const float m = bf_hi(o[e]);
          dsum += (b == NMAIN + 2 ? rbf(1.f + m) : m) * ((e & 1) ? bf_hi(wv[e >> 1]) : bf_lo(wv[e >> 1]));
        }
#pragma unroll
        for (int k = 16; k > 0; k >>= 1) dsum += __shfl_xor_sync(0xffffffffu, dsum, k);
        if (lane == 0) st_relaxed(g_mod + (b - NMAIN) * 4 + warp, tagf(dsum, tag));
      }
    }
    PROF(2, tid == 0, 1);
    return;
  }

  const int rank = b & 1;
  const int rb = ((b >> 4) << 1) | rank, cj = (b >> 1) & 7;
  const uint32_t bfull = base + OFF_BAR, bempty = bfull + NSLOT * 8;
  const uint32_t gfull = bempty + NSLOT * 8, gempty = gfull + 32;
  const uint32_t bar_ofull = gempty + 32;
  const uint32_t bar_ofree = bar_ofull + 32;
  const uint32_t bar_par = bar_ofree + 32;
  const uint32_t bar_mod = bar_par + 8;
  const uint32_t bar_pread = bar_mod + 8;
  const uint32_t bar_xres = bar_pread + 8;
  const uint32_t bar_ring = bar_xres + 8;
  const uint32_t bar_box = bar_ring + 24;
  const uint32_t bar_go = bar_box + 96;
  const uint32_t bar_go2 = bar_go + 16;
  const uint32_t bar_cnt = bar_go + 24;
  const uint32_t xfull = bar_go + 32, xempty = xfull + 32;
  const uint32_t bar_hw = xempty + 32, bar_hx = bar_hw + 8;
  const uint32_t bar_hpub = bar_hx + 16;
  const uint32_t bar_win = bar_hpub + 8;
  const uint32_t bar_rx = bar_win + 8;
  const uint32_t bar_sel = bar_rx + 8;
  const uint32_t bar_gate = bar_sel + 8;
  const uint32_t bar_rel = bar_gate + 8;
  const uint32_t bar_od = bar_rel + 8;
  const uint32_t bar_res = bar_go + 8;
  const uint32_t stage = base + OFF_STAGE, par = base + OFF_PAR;

  if (warp == 8 && elect_one()) {
    for (int s = 0; s < NSLOT; s++) { mbar_init(bfull + s * 8, 1); mbar_init(bempty + s * 8, 16); }
    for (int s = 0; s < 4; s++) { mbar_init(gfull + s * 8, 1); mbar_init(gempty + s * 8, 16); mbar_init(xfull + s * 8, 1); mbar_init(xempty + s * 8, 8); mbar_init(bar_ofree + s * 8, 1); mbar_init(bar_ofull + s * 8, 128); }
    mbar_init(bar_par, 64); mbar_init(bar_mod, 256); mbar_init(bar_pread, 8); mbar_init(bar_xres, 1);
    mbar_init(bar_ring, 8); mbar_init(bar_ring + 8, 8); mbar_init(bar_ring + 16, 8);
    mbar_init(bar_go, 1); mbar_init(bar_go2, 1); mbar_init(bar_cnt, 1); mbar_init(bar_hpub, 8); mbar_init(bar_res, 1); mbar_init(bar_win, 1); mbar_init(bar_rx, 1); mbar_init(bar_sel, 64); mbar_init(bar_gate, 8); mbar_init(bar_rel, 8); mbar_init(bar_od, 1);
    for (int s = 0; s < 12; s++) mbar_init(bar_box + s * 8, 1);
    asm volatile("fence.mbarrier_init.release.cluster;" ::: "memory");
    prefetch_map(&maps.x); prefetch_map(&maps.wq); prefetch_map(&maps.k); prefetch_map(&maps.v);
  }
  if (warp == 9 && elect_one()) {
    mbar_init(bar_hw, 1); mbar_init(bar_hx, 1); mbar_init(bar_hx + 8, 1);
    asm volatile("fence.mbarrier_init.release.cluster;" ::: "memory");
    mbar_expect_tx(bar_hw, 32768);
    mbar_expect_tx(bar_hx, 16384);
    mbar_expect_tx(bar_hx + 8, 16384);
    const __nv_bfloat16* xs = P.x + (size_t)(rb * 128 + cj * 16) * DM;
    bulk_load(base + 2 * GST_BYTES, xs, 16384, bar_hx);
    tma2d(stage, &maps.wm, (b >> 1) * 32, rank * 512, bar_hw);
    tma2d(stage + 16384, &maps.wm, (b >> 1) * 32, rank * 512 + 256, bar_hw);
    bulk_load(base + 3 * GST_BYTES, xs + 8 * DM, 16384, bar_hx + 8);
  }
  cluster_arrive();

  if (warp >= 8) {
    asm volatile("setmaxnreg.dec.sync.aligned.u32 40;");
    if (warp < 10) bar_arrive(1, 320);
    const uint32_t epoch = ld_relaxed(&g_epoch);
    cluster_wait();
    if (warp == 8) {
      const int kvrow = (cj >> 1) * SK + (SK - WIN);
      int wch = cj * 8 + rank * 2;
#pragma unroll 1
      for (int ps = 0; ps < 3; ps++) {
        const CUtensorMap* mw = ps == 2 ? &maps.wo : &maps.wq;
        const uint32_t xt = ps == 1 ? XT1 : XT2, wt = ps == 0 ? WT0 : (ps == 1 ? WT1 : WT2);
        const int nst = ps == 2 ? 32 : 16;
#pragma unroll 1
        for (int i = 0; i < nst; i++) {
          const uint32_t bf = gfull + (i & 3) * 8;
          const int kt = ps == 2 ? (((cj & 1) * 4 + ((i >> 1) & 3)) * 4 + (i >> 3)) * 2 + (i & 1) : (i + (ps ? 0 : b & 14)) & 15;
          const uint32_t wd = base + unit_of(wt, i & 3) + rank * UNIT, xd = base + unit_of(xt, i & 3);
          const uint8_t* xs = g_act + (uint32_t)(rb * 80 + (ps - 1) * 16 + kt) * UNIT;
          if (ps == 0 && i == HD) mbar_wait(bar_mod, 0);
          const bool xfirst = ps && i < 2;
          if (ps == 2 && i == 0) mbar_wait(bar_ofree + 24, 0);
          if (i == 0) fence_async();
          mbar_wait(gempty + (i & 3) * 8, ((i >> 2) & 1) ^ 1);
          if (elect_one()) {
            mbar_expect_tx(bf, ps ? GST_BYTES : 2 * UNIT);
            if (xfirst) bulk_load_stream(xd, xs, UNIT, bf);
          }
          if (ps && i < 4) mbar_wait(bempty + i * 8, 1);
          if (elect_one()) tma3d_mc<true>(wd, mw, 0, (i == 31 ? kt ^ (rank * 32) : kt) * 64, i == 31 ? cj * 2 : wch, bf);
          if (ps) {
            if (i == 16) { mbar_wait(bar_cnt, 0); fence_async(); }
            if (i == 2) mbar_wait(bar_ofree + (ps - 1) * 16, 0);
            if (elect_one()) {
              if (i == 31) bulk_load(xd, xs, UNIT, bf); else if (!xfirst) bulk_load_stream(xd, xs, UNIT, bf);
              mbar_arrive_pred(bar_go, i == GOST - 1);
              mbar_arrive_pred(bar_od, i == ODS);
              mbar_arrive_pred(bar_res, ((1u << RES0 | 1u << RES1) >> i) & 1);
            }
          }
        }
        if (ps == 2) break;
        wch = ps ? ((wch >> 3) ^ rank) * 2 : wch + 4;
#pragma unroll 1
        for (int u = 0; u < 16; u++) {
          const bool isk = (u == 0) || ((u & 1) && u < 15);
          const int blk = (isk ? (u + 1) >> 1 : (u == 15 ? 7 : (u >> 1) - 1)) & 3;
          const uint32_t sl = base + unit_of(ps ? AT1 : AT0, u & 3) + rank * UNIT, bf = bfull + (u & 3) * 8;
          if (u < 4) mbar_wait(gempty + ((u + 1) >> 1) * 8, 1);
          mbar_wait(bempty + (u & 3) * 8, ((u >> 2) & 1) ^ 1);
          if (elect_one()) {
            mbar_arrive_pred(bar_go2, ps && u == PG0);
            mbar_expect_tx(bf, SLOT_BYTES);
            tma3d_mc<false>(sl, isk ? &maps.k : &maps.v, 0, kvrow + blk * 128, rank, bf);
          }
        }
      }
      if (elect_one()) mbar_expect_tx(bar_rx, UNIT);
      mbar_wait(bar_rel, 0);
      if (elect_one()) {
        bulk_load_stream(base + UNIT, g_act + (uint32_t)(rb * 80 + 16 + 63 - (cj & 1) * 32) * UNIT, UNIT, bar_rx);
      }
      if (b < NFFN) {
#pragma unroll 1
        for (int u = 0; u < 12; u++) {
          const uint32_t dst = base + unit_of(u < 4 ? FT_G : (u < 8 ? FT_U : FT_D), u & 3);
          if (elect_one()) mbar_expect_tx(bar_box + u * 8, UNIT);
          if (u == FB0 || u == 2 || u == FB2) mbar_wait(bar_ring + (u == FB2 ? 16 : (u + 6) & 8), 0);
          if (u >= FPACE) mbar_wait(bar_box + (u - FPACE) * 8, 0);
          if (elect_one()) {
            if (u < 8) tma2d(dst, u < 4 ? &maps.wg : &maps.wu, b * 32, (u & 3) * 256, bar_box + u * 8);
            else tma3d(dst, &maps.wd, 0, b * 32, (u - 8) * 4, bar_box + u * 8);
          }
        }
      }
    } else if (warp == 9) {
      const uint32_t target = 8 * (epoch + 1);
#pragma unroll 1
      for (int i = 0; i < 16; i++) {
        if (i == HDX) mbar_wait(bar_mod, 0);
        if (i == NRS) {
          wait_counter(&g_cnt_h[rb * 32], target);
          PROF(1, lane == 0, 26);
          fence_async();
        }
        mbar_wait(xempty + (i & 3) * 8, ((i >> 2) & 1) ^ 1);
        if (elect_one()) {
          mbar_expect_tx(xfull + (i & 3) * 8, UNIT);
          if (i < NRS) tma2d(base + (i & 3) * GST_BYTES, &maps.x, ((2 * cj + i) & 15) * 64, rb * 128, xfull + (i & 3) * 8);
          else bulk_load_stream(base + (i & 3) * GST_BYTES, g_act + (uint32_t)(rb * 80 + ((2 * cj + i) & 15)) * UNIT, UNIT, xfull + (i & 3) * 8);
        }
      }
      prefetch_map(&maps.wo);
#pragma unroll 1
      for (int t = 0; t < 4; t++) {
        if (t & 1) mbar_wait(bar_od, t >> 1);
#pragma unroll 1
        for (int p = 0; p < 32768 / OPS; p++) {
          const uint32_t w = p / (16384 / OPS), c = (p / (8192 / OPS)) & 1, off = w * 8192 + (p % (8192 / OPS)) * OPS;
          mbar_wait(bar_ofull + (t & 1) * 16 + w * 8, t >> 1);
          if (elect_one()) {
            bulk_store(g_act + (uint32_t)(rb * 80 + 16 + (cj * 4 + t) * 2 + c) * UNIT + off, base + unit_of(QT, 2 * t + c) + off, OPS);
            asm volatile("cp.async.bulk.commit_group;" ::: "memory");
            asm volatile("cp.async.bulk.wait_group.read %0;" ::"n"(OFL) : "memory");
          }
        }
        if (elect_one()) {
          asm volatile("cp.async.bulk.wait_group.read 0;" ::: "memory");
          mbar_arrive_pred(bar_ofree + t * 8, t < 3);
          asm volatile("cp.async.bulk.wait_group 0;" ::: "memory");
          fence_async();
          red_release(&g_cnt_o[((rb * 4 + t) * 2 + (cj >> 2)) * 32], 2);
        }
        if (t & 1) {
          wait_counter(&g_cnt_o[(rb * 8 + 2 * t - 2 + (cj & 1)) * 32], target);
          wait_counter(&g_cnt_o[(rb * 8 + 2 * t + (cj & 1)) * 32], target);
          if (elect_one()) mbar_arrive_pred(bar_ofree + 24, t == 1);
        }
      }
      wait_counter(&g_cnt_o[(rb * 8 + 7 - (cj & 1)) * 32], target);
      fence_async();
      if (elect_one()) {
        mbar_arrive(bar_cnt);
        PROF(2, true, 27);
        mbar_expect_tx(bar_xres, 32768);
      }
#pragma unroll 1
      for (int u = 0; u < 2; u++) {
        mbar_wait(bar_res, u);
        if (elect_one()) tma2d(base + OFF_RES + u * UNIT, &maps.x, cj * 128 + u * 64, rb * 128, bar_xres);
      }
      const uint32_t tag = epoch % 3 + 1;
      const uint32_t* inbox = g_cand + (lane & 15);
      mbar_wait(bar_ring + 16, 0);
      uint32_t c0 = ld_relaxed(inbox), n = 0;
#define CAND_STEP(cv)                                                                                        \
      {                                                                                                      \
        const bool valid = (cv & 3u) == tag, all = __all_sync(0xffffffffu, valid);                           \
        const uint32_t best = __reduce_max_sync(0xffffffffu, valid ? cv : 0u);                               \
        const uint32_t blk = __ffs(__ballot_sync(0xffffffffu, cv == best)) - 1;                              \
        if (best) sts2(par + PAR_CONST + 56, best, (blk << 7 | (~best >> 2 & 127)) | (all ? 0x1800 : 0x800)); \
        if (all) break;                                                                                      \
        cv = ld_relaxed(inbox);                                                                              \
      }
      while (true) { CAND_STEP(c0) watchdog(n); }
    } else {
      const int t2 = tid - 320;
      if (t2 == 0) {
        mbar_wait(bar_hpub, 0);
        PROF(1, true, 24);
        red_release(&g_cnt_h[rb * 32], 1);
        PROF(1, true, 25);
        prefetch_map(&maps.wg); prefetch_map(&maps.wu); prefetch_map(&maps.wd); prefetch_map(&maps.out);
      }
      __syncwarp();
      if (b < NFFN) {
        mbar_wait(bar_go2, 0);
        const __nv_bfloat16* pg = ((b & 1) ? P.w_up : P.w_gate) + (b >> 1) * 64 + (size_t)t2 * FF;
        const __nv_bfloat16* pd = P.w_down + (size_t)b * 32768 + t2 * 64;
        PROF(2, t2 == 0, 13);
#pragma unroll 1
        for (int i = 0; i < WN; i += WB) {
          uint32_t v[WB];
#pragma unroll
          for (int u = 0; u < WB; u++) {
            const int k = i + u;
            asm volatile("ld.global.cg.L2::128B.u32 %0, [%1];" : "=r"(v[u]) : "l"(k < 16 ? pg + (size_t)k * 64 * FF : pd + (k - 16) * 4096));
          }
#pragma unroll
          for (int u = 1; u < WB; u++) v[0] ^= v[u];
          sts1(par + PAR_SINK + t2 * 4, v[0]);
        }
        PROF(2, t2 == 0, 14);
      }
      const uint32_t tag = epoch % 3 + 1;
      mbar_wait(bar_go, 0);
      if (warp == 10) {
        const uint32_t* src = g_mod + 2 * DM + cj * 128 + lane * 4;
        const uint2 wr = *reinterpret_cast<const uint2*>(P.w_r + cj * 128 + lane * 4);
        uint4 vga, vsb, vcb, vgb;
        uint32_t n = 0;
        do {
          vga = ld_relaxed4(src); vsb = ld_relaxed4(src + DM); vcb = ld_relaxed4(src + 2 * DM); vgb = ld_relaxed4(src + 3 * DM);
          watchdog(n);
        } while (!(tag_ok(vga, tag) && tag_ok(vsb, tag) && tag_ok(vcb, tag) && tag_ok(vgb, tag)));
        const float c0 = rbf(1.f + bf_hi(vcb.x)), c1 = rbf(1.f + bf_hi(vcb.y)), c2 = rbf(1.f + bf_hi(vcb.z)), c3 = rbf(1.f + bf_hi(vcb.w));
        const float a0 = c0 * bf_lo(wr.x), a1 = c1 * bf_hi(wr.x), a2 = c2 * bf_lo(wr.y), a3 = c3 * bf_hi(wr.y);
        const uint32_t h0 = pack_bf(a0, a1), h1 = pack_bf(a2, a3);
        const uint32_t t1 = par + PAR_T1 + (lane >> 2) * 64 + (lane & 1) * 32 + (lane & 2) * 2;
        sts1(t1, h0); sts1(t1 + 8, pack_bf(a0 - bf_lo(h0), a1 - bf_hi(h0)));
        sts1(t1 + 16, h1); sts1(t1 + 24, pack_bf(a2 - bf_lo(h1), a3 - bf_hi(h1)));
        sts4(par + PAR_T2 + lane * 32, make_uint4(pack_bf(c0, c1), __byte_perm(vsb.x, vsb.y, 0x7632), __byte_perm(vgb.x, vgb.y, 0x7632), __byte_perm(vga.x, vga.y, 0x7632)));
        sts4(par + PAR_T2 + lane * 32 + 16, make_uint4(pack_bf(c2, c3), __byte_perm(vsb.z, vsb.w, 0x7632), __byte_perm(vgb.z, vgb.w, 0x7632), __byte_perm(vga.z, vga.w, 0x7632)));
      } else if (lane < 4) {
        const uint4 g = poll4(lane < 2 ? g_mod + 5 * DM + b * 8 + lane * 4 : g_mod + 16 - lane * 4, tag);
        sts1(par + PAR_CONST + 60, 0);
        if (lane < 2) sts4(par + PAR_CONST + 16 + lane * 16, g);
        else sts2(par + PAR_CONST + (lane - 2) * 8, __float_as_uint(untag_sum(g.x, g.y) + untag_sum(g.z, g.w)), epoch);
      }
      __syncwarp();
#pragma unroll 4
      for (int q = XR; q < XE; q++) st_b128(g_xch + ((size_t)b * 8 * 256 + q * 64 + t2) * 4, (epoch & 1) << 16, 0, 0, 0);
      for (int q = 0; q < 2; q++) st_relaxed4(g_stats + ((size_t)cj * SEQ + rb * 128 + q * 64 + t2) * 4, 0, 0, 0, 0);
      if (b < NFFN)
        for (int q = 0; q < 4; q++) st_relaxed4(g_ypart + ((size_t)(q * 32 + (t2 >> 1)) * NFFN + b) * 8 + (t2 & 1) * 4, 0, 0, 0, 0);
      st_relaxed4(g_row + rb * 2 * DM + (t2 >> 5) * DM + cj * 128 + (t2 & 31) * 4, 0, 0, 0, 0);
      __threadfence();
      mbar_arrive(bar_par);
      mbar_wait(bar_gate, 0);
      uint32_t have = 0, n = 0;
      while (true) {
        const uint32_t st = lds1(par + PAR_CONST + 60) >> 7;
        if ((st & 31) != have) {
          const uint32_t* hsrc = g_row + (st & 15) * 2 * DM + t2 * 4;
          uint4 hv[4];
          bool ok = true;
#pragma unroll
          for (int i = 0; i < 4; i++) hv[i] = ld_pairs(hsrc + i * 256);
#pragma unroll
          for (int i = 0; i < 4; i++) {
            sts2(base + ((FT_G >> i * 4) & 15) * UNIT + (warp & 1) * 8192 + 256 + lane * 8, hv[i].x, hv[i].z);
            ok = ok && hv[i].y == tag && hv[i].w == tag;
          }
          have = __all_sync(0xffffffffu, ok) ? st & 31 : 0;
        }
        if ((st ^ have) == 32) break;
        watchdog(n);
      }
      mbar_arrive(bar_sel);
    }
    __syncwarp();
    cluster_arrive();
    {
      const uint32_t tag = epoch % 3 + 1, t3 = tid - 256;
      mbar_wait(bar_win, 0);
      uint2 win = lds2(par + PAR_CONST + 56);
      win.y &= 0x7ff;
      const uint32_t* fsrc = g_row + (win.y >> 7) * 2 * DM + (b >> 1) * 16 + (t3 & 3) * 4 + (b & 1) * 2;
      const uint32_t* ysrc = g_ypart + (size_t)b * NFFN * 8 + min(t3, NFFN - 1) * 4;
      uint2 fh = ld_pair(fsrc), fx = ld_pair(fsrc + DM);
      if (PSL) __nanosleep(PSL);
      uint4 ya = ld_relaxed4(ysrc), yb = ld_relaxed4(ysrc + NFFN * 4);
      const float rwin = __uint_as_float(((int)win.x < 0 ? win.x & 0x7fffffffu : ~win.x) & ~0x1ffu);
      const float rs = rbf(rcp(1.f + __expf(-rbf(rwin))));
      uint32_t n = 0;
      while (fh.y != tag || fx.y != tag) { fh = ld_pair(fsrc); fx = ld_pair(fsrc + DM); watchdog(n); }
      while (!(tag_ok(ya, tag) && tag_ok(yb, tag))) {
        if (!tag_ok(ya, tag)) ya = ld_relaxed4(ysrc);
        if (!tag_ok(yb, tag)) yb = ld_relaxed4(ysrc + NFFN * 4);
        watchdog(n);
      }
      __syncwarp();
      PROF(8, t3 == 0, 5);
      float y0 = untag_sum(ya.x, yb.x), y1 = untag_sum(ya.y, yb.y), y2 = untag_sum(ya.z, yb.z), y3 = untag_sum(ya.w, yb.w);
      const bool u1 = lane & 2, u2 = lane & 4;
      y0 = (u1 ? y2 : y0) + __shfl_xor_sync(0xffffffffu, u1 ? y0 : y2, 2);
      y1 = (u1 ? y3 : y1) + __shfl_xor_sync(0xffffffffu, u1 ? y1 : y3, 2);
      y0 = (u2 ? y1 : y0) + __shfl_xor_sync(0xffffffffu, u2 ? y0 : y1, 4);
      y0 += __shfl_xor_sync(0xffffffffu, y0, 8);
      if (!(lane & 8)) sts1(par + PAR_RED + 64 + (t3 >> 4) * 32 + ((lane & 1) * 4 + (lane & 2) + ((lane >> 2) & 1)) * 4, __float_as_uint(y0));
      bar_sync(4, 128);
      if (t3 < 4) {
        y0 = 0.f; y1 = 0.f;
#pragma unroll
        for (int w4 = 0; w4 < 7; w4++) {
          const uint2 v = lds2(par + PAR_RED + 64 + w4 * 32 + t3 * 8);
          y0 += __uint_as_float(v.x); y1 += __uint_as_float(v.y);
        }
        const uint2 gv = lds2(par + PAR_CONST + 16 + t3 * 8);
        const uint32_t upd = hmul2(pack_bf(y0, y1), pack_bf(rs, rs));
        *reinterpret_cast<uint32_t*>(P.out + (size_t)win.y * DM + b * 8 + t3 * 2) =
            hadd2(fx.x, hmul2(__byte_perm(gv.x, gv.y, 0x7632), hadd2(fh.x, upd)));
        if (b == 0 && t3 == 0) st_relaxed(&g_epoch, epoch + 1);
      }
      PROF(31, t3 == 0, 36);
    }
    cluster_wait();
  } else {
    const int wg = warp >> 2;

    uint32_t tag;
    {
      uint32_t* const pmod = g_modp + rank * 2 * DM + (b >> 1) * 32 + lane;
      uint32_t* const pln = g_ln1 + (rb * 128 + cj * 16 + warp) * 4;
      const uint32_t cv = ldg_nc1(P.c + rank * 512 + tid * 2);
      const uint32_t epoch = ld_relaxed(&g_epoch);
      if (warp == 0) st_relaxed(pmod, 0);
      if (lane == 0) { st_b128(pln, 0, 0, 0, 0); st_b128(pln + 32, 0, 0, 0, 0); }
      asm volatile("setmaxnreg.inc.sync.aligned.u32 232;");
      sts1(par + tid * 4, pack_bf(silu_f(bf_lo(cv)), silu_f(bf_hi(cv))));
      bar_sync(1, 320);
      tag = epoch % 3 + 1;
#pragma unroll
      for (int part = 0; part < 3; part++) {
        if (part != 1) {
          const uint32_t xa = base + (2 + part / 2) * GST_BYTES + warp * 2048 + lane * 16;
          mbar_wait(bar_hx + part * 4, 0);
          float s0 = 0.f, s1 = 0.f, q0 = 0.f, q1 = 0.f;
#pragma unroll
          for (int q = 0; q < 4; q++) {
            const uint4 xv = lds4(xa + q * 512);
            const uint32_t u[4] = {xv.x, xv.y, xv.z, xv.w};
#pragma unroll
            for (int e = 0; e < 4; e++) { const float lo = bf_lo(u[e]), hi = bf_hi(u[e]); s0 += lo; s1 += hi; q0 += lo * lo; q1 += hi * hi; }
          }
          s0 += s1; q0 += q1;
#pragma unroll
          for (int o = 16; o > 0; o >>= 1) { s0 += __shfl_xor_sync(0xffffffffu, s0, o); q0 += __shfl_xor_sync(0xffffffffu, q0, o); }
          const float mean = s0 * (1.f / DM);
          float mb, sd;
          ln_scalars(mean, fmaxf(q0 * (1.f / DM) - mean * mean, 0.f), mb, sd);
          uint32_t ih, il;
          split_inv(sd, ih, il);
          if (lane == 0) st_b128(pln + part * 16, pack_bf(mb, mb), ih, il, tag);
          PROF(1, tid == 0 && part == 2, 4);
        } else {
          float acc[8];
#pragma unroll
          for (int e = 0; e < 8; e++) acc[e] = 0.f;
          const uint32_t wa = stage + (tid >> 2) * 64 + (((tid ^ (tid >> 3)) & 3) << 4), sa = par + (tid >> 3) * 4, sh = (tid & 4) ? 0x3244 : 0x1044;
          mbar_wait(bar_hw, 0);
#pragma unroll
          for (int p = 0; p < 8; p++) {
            const uint4 w = lds4(wa + p * 4096);
            const float s = __uint_as_float(__byte_perm(lds1(sa + p * 128), 0, sh));
            acc[0] += s * bf_lo(w.x); acc[1] += s * bf_hi(w.x); acc[2] += s * bf_lo(w.y); acc[3] += s * bf_hi(w.y);
            acc[4] += s * bf_lo(w.z); acc[5] += s * bf_hi(w.z); acc[6] += s * bf_lo(w.w); acc[7] += s * bf_hi(w.w);
          }
#pragma unroll
          for (int e = 0; e < 4; e++) {
            const bool up = lane & 16;
            acc[e] = (up ? acc[e + 4] : acc[e]) + __shfl_xor_sync(0xffffffffu, up ? acc[e] : acc[e + 4], 16);
          }
#pragma unroll
          for (int e = 0; e < 2; e++) {
            const bool up = lane & 8;
            acc[e] = (up ? acc[e + 2] : acc[e]) + __shfl_xor_sync(0xffffffffu, up ? acc[e] : acc[e + 2], 8);
          }
          {
            const bool up = lane & 4;
            acc[0] = (up ? acc[1] : acc[0]) + __shfl_xor_sync(0xffffffffu, up ? acc[0] : acc[1], 4);
          }
          sts1(par + 1024 + warp * 128 + ((lane & 3) * 8 + (lane >> 2)) * 4, __float_as_uint(acc[0]));
          bar_sync(1, 256);
          if (warp == 0) {
            float s = 0.f;
#pragma unroll
            for (int w8 = 0; w8 < 8; w8++) s += __uint_as_float(lds1(par + 1024 + w8 * 128 + lane * 4));
            st_relaxed(pmod, (__float_as_uint(s) & ~3u) | tag);
          }
          PROF(1, tid == 0, 3);
        }
      }
      cluster_wait();
      if (wg == 1) bar_arrive(2, 256);
    }

    float f0 = 0.f, f1 = 0.f;
    const uint32_t rempty = lane < 2 ? mapa(bempty, lane & 1) : 0;
    constexpr uint32_t GE = NSLOT * 8 + 32;
    float o[64], s[64];
#pragma unroll 1
    for (int ps = 0; ps < 3; ps++) {
      {
        const uint32_t xt = ps == 1 ? XT1 : XT2, wt = ps == 1 ? WT1 : WT2;
        const int nst = ps == 2 ? 28 : 14;
        if (ps == 0) {
          float ga[64], gb[64];
#pragma unroll
          for (int i = 0; i < 64; i++) { ga[i] = 0.f; gb[i] = 0.f; }
          uint32_t a[2][16];
          const uint32_t l = fresh_lane();
          auto fetch = [&](int i, uint32_t (&f)[16], uint32_t z) {
            const uint32_t ad = base + (i & 3) * GST_BYTES + wg * 8192 + frag_offset(warp) + z;
            mbar_wait(xfull + (i & 3) * 8, i >> 2);
#pragma unroll
            for (int kk = 0; kk < 4; kk++) ldmatrix4(ad ^ (kk * 32), f[4 * kk], f[4 * kk + 1], f[4 * kk + 2], f[4 * kk + 3]);
          };
          uint4 r0, r1;
          {
            const uint32_t t7 = (warp & 3) * 32 + l;
            const uint32_t* pm = g_modp + wg * DM + ((cj * 128 + t7 * 4) & (DM - 1));
            const uint32_t* pr = g_ln1 + (rb * 128 + warp * 16 + (l >> 2)) * 4;
            uint4 m0 = ld_relaxed4(pm), m1 = ld_relaxed4(pm + 2 * DM);
            r0 = ld_b128(pr); r1 = ld_b128(pr + 32);
            fetch(0, a[0], 0); fetch(1, a[1], 0);
            uint32_t n = 0;
            bool written = false;
#pragma unroll 1
            while (true) {
              uint32_t miss;
              asm volatile("{ .reg .pred p0, p1, p2, p3; .reg .b32 t, u;\n"
                           "lop3.b32 t, %1, %2, %19, 0x7e; lop3.b32 u, %3, %4, %19, 0x7e; or.b32 t, t, u; and.b32 t, t, 3; setp.ne.u32 p0, t, 0;\n"
                           "lop3.b32 t, %5, %6, %19, 0x7e; lop3.b32 u, %7, %8, %19, 0x7e; or.b32 t, t, u; and.b32 t, t, 3; setp.ne.u32 p1, t, 0;\n"
                           "setp.ne.u32 p2, %12, %19; setp.ne.u32 p3, %16, %19;\n"
                           "@p0 ld.relaxed.gpu.global.v4.u32 {%1, %2, %3, %4}, [%17];\n"
                           "@p1 ld.relaxed.gpu.global.v4.u32 {%5, %6, %7, %8}, [%17 + 8192];\n"
                           "@p2 ld.relaxed.gpu.global.v4.u32 {%9, %10, %11, %12}, [%18];\n"
                           "@p3 ld.relaxed.gpu.global.v4.u32 {%13, %14, %15, %16}, [%18 + 128];\n"
                           "or.pred p0, p0, p1; or.pred p2, p2, p3; vote.sync.any.pred p0, p0, 0xffffffff; vote.sync.any.pred p2, p2, 0xffffffff;\n"
                           "selp.u32 t, 1, 0, p0; selp.u32 u, 2, 0, p2; or.b32 %0, t, u; }"
                           : "=r"(miss), "+r"(m0.x), "+r"(m0.y), "+r"(m0.z), "+r"(m0.w), "+r"(m1.x), "+r"(m1.y), "+r"(m1.z), "+r"(m1.w),
                             "+r"(r0.x), "+r"(r0.y), "+r"(r0.z), "+r"(r0.w), "+r"(r1.x), "+r"(r1.y), "+r"(r1.z), "+r"(r1.w)
                           : "l"(pm), "l"(pr), "r"(tag) : "memory");
              if (!(miss & 1) && !written) {
                written = true;
                float c0 = untag_sum(m0.x, m1.x), c1 = untag_sum(m0.y, m1.y), c2 = untag_sum(m0.z, m1.z), c3 = untag_sum(m0.w, m1.w);
                if (wg) { c0 = 1.f + rbf(c0); c1 = 1.f + rbf(c1); c2 = 1.f + rbf(c2); c3 = 1.f + rbf(c3); }
                const uint32_t d = stage + (t7 >> 2) * 64 + (t7 & 1) * 32 + (t7 & 2) * 2 + (wg ? 0 : 8);
                sts1(d, pack_bf(c0, c1));
                sts1(d + 16, pack_bf(c2, c3));
                mbar_arrive(bar_mod);
              }
              if (!miss) break;
              watchdog(n);
            }
          }
          const uint32_t zero = r0.w ^ tag;
          auto normalize = [&](uint32_t (&f)[16]) {
#pragma unroll
            for (int k = 0; k < 16; k += 2) { f[k] = ln_norm(f[k], r0.x, r0.y, r0.z); f[k + 1] = ln_norm(f[k + 1], r1.x, r1.y, r1.z); }
          };
          auto modulate = [&](int i, uint32_t (&f)[16]) {
#pragma unroll
            for (int kk = 0; kk < 4; kk++) {
              const uint4 m = lds4(stage + (l & 3) * 16 + i * 256 + kk * 64);
              f[4 * kk] = modul(f[4 * kk], m.x, m.z); f[4 * kk + 1] = modul(f[4 * kk + 1], m.x, m.z);
              f[4 * kk + 2] = modul(f[4 * kk + 2], m.y, m.w); f[4 * kk + 3] = modul(f[4 * kk + 3], m.y, m.w);
            }
            keep(f);
            mbar_arrive_pred(xempty + (i & 3) * 8, l == 0);
          };
          auto publish = [&](int u, uint32_t (&f)[16]) {
            const uint32_t sc = stage + 8192 + wg * 8192;
#pragma unroll
            for (int kk = 0; kk < 4; kk++) stmatrix4((sc + frag_offset(warp)) ^ (kk * 32), f[4 * kk], f[4 * kk + 1], f[4 * kk + 2], f[4 * kk + 3]);
            __syncwarp();
            const uint32_t src = sc + (warp & 3) * 2048 + l * 16;
            uint8_t* dst = g_act + (uint32_t)(rb * 80 + cj * 2 + u) * UNIT + warp * 2048 + l * 16;
#pragma unroll
            for (int p4 = 0; p4 < 4; p4++) stg4(dst + p4 * 512, lds4(src + p4 * 512));
            __syncwarp();
            if (u == 1) mbar_arrive_pred(bar_hpub, l == 0);
          };
          auto multiply = [&](int i, uint32_t (&f)[16]) {
            mbar_wait(gfull + (i & 3) * 8, i >> 2);
            const uint64_t db = make_desc(base + (i & 3) * GST_BYTES + UNIT, 8192, 1024);
            wg_fence();
#pragma unroll
            for (int kk = 0; kk < 4; kk++) mma256_rs(ga, gb, f[4 * kk], f[4 * kk + 1], f[4 * kk + 2], f[4 * kk + 3], db + kk * 128);
            wg_commit();
          };
          auto next = [&](int i, uint32_t (&f)[16]) {
            wg_wait<1>();
            mbar_arrive_cl(rempty, GE + ((i + 2) & 3) * 8);
            uint32_t z = zero;
#pragma unroll
            for (int k = 0; k < 16; k += 2) asm volatile("lop3.b32 %0, %1, %2, %0, 0xA8;" : "+r"(z) : "r"(f[k]), "r"(f[k + 1]));
            fetch(i, f, z); normalize(f); modulate(i, f); multiply(i, f);
          };
          normalize(a[0]); normalize(a[1]);
          keep(a[0]); keep(a[1]);
          mbar_wait(bar_mod, 0);
          PROF(1, tid == 0, 2);
          if (PORD == 0) { modulate(0, a[0]); multiply(0, a[0]); modulate(1, a[1]); multiply(1, a[1]); publish(0, a[0]); publish(1, a[1]); }
          if (PORD == 1) { modulate(0, a[0]); multiply(0, a[0]); publish(0, a[0]); modulate(1, a[1]); multiply(1, a[1]); publish(1, a[1]); }
          if (PORD == 2) { modulate(0, a[0]); multiply(0, a[0]); publish(0, a[0]); modulate(1, a[1]); publish(1, a[1]); multiply(1, a[1]); }
#pragma unroll 1
          for (int i = 2; i < NRS; i += 2) { next(i, a[0]); next(i + 1, a[1]); }
          wg_wait<1>();
          mbar_arrive_cl(rempty, GE + ((NRS + 2) & 3) * 8);
          mbar_arrive_pred(bar_pread, l == 0);
#pragma unroll 1
          for (int i = NRS; i < 14; i++) {
            mbar_wait(xfull + (i & 3) * 8, (i >> 2) & 1);
            mbar_wait(gfull + (i & 3) * 8, (i >> 2) & 1);
            const uint32_t xa = base + (i & 3) * GST_BYTES;
            const uint64_t da = make_desc(xa + wg * 8192, 16, 1024), db = make_desc(xa + UNIT, 8192, 1024);
            if (i == 13) bar_sync(2 + wg, 256);
            wg_fence();
#pragma unroll
            for (int kk = 0; kk < 4; kk++) mma256_ss(ga, gb, da + kk * 2, db + kk * 128, 1);
            wg_commit();
            if (i == 13) bar_arrive(3 - wg, 256);
            wg_wait<1>();
            uint32_t z = zero;
#pragma unroll
            for (int k = 0; k < 16; k += 2) asm volatile("lop3.b32 %0, %1, %2, %0, 0xA8;" : "+r"(z) : "r"(a[1][k]), "r"(a[1][k + 1]));
            mbar_arrive_cl(rempty, GE + ((i + 3) & 3) * 8 + z);
            mbar_arrive_pred(xempty + ((i + 3) & 3) * 8, l == 0 && i != NRS);
          }
          mbar_wait(xfull + 16, 1);
          wg_wait<0>();
          keep(ga); keep(gb);
#pragma unroll
          for (int i = 0; i < 64; i++) {
            asm volatile("mov.b32 %0, %1;" : "=f"(s[i]) : "f"(ga[i]));
            asm volatile("mov.b32 %0, %1;" : "=f"(o[i]) : "f"(gb[i]));
          }
        } else {
          float ga[64], gb[64];
#pragma unroll
          for (int i = 0; i < 64; i++) {
            asm volatile("mov.b32 %0, %1;" : "=f"(ga[i]) : "f"(s[i]));
            asm volatile("mov.b32 %0, %1;" : "=f"(gb[i]) : "f"(o[i]));
          }
#pragma unroll 1
          for (int i = 0; i < nst; i++) {
            mbar_wait(gfull + (i & 3) * 8, (i >> 2) & 1);
            const uint64_t da = make_desc(base + unit_of(xt, i & 3) + wg * 8192, 16, 1024), db = make_desc(base + unit_of(wt, i & 3), 8192, 1024);
            if (i == nst - 1) bar_sync(2 + wg, 256);
            wg_fence();
#pragma unroll
            for (int kk = 0; kk < 4; kk++) mma256_ss(ga, gb, da + kk * 2, db + kk * 128, kk ? 1 : i);
            wg_commit();
            if (i == nst - 1) bar_arrive(3 - wg, 256);
            wg_wait<1>();
            mbar_arrive_cl(rempty, GE + ((i + 3) & 3) * 8, i != 0);
            PROF(4, tid == 0 && (i & 3) == 0, 40 + (ps - 1) * 4 + i / 4);
          }
          wg_wait<0>();
          keep(ga); keep(gb);
#pragma unroll
          for (int i = 0; i < 64; i++) {
            asm volatile("mov.b32 %0, %1;" : "=f"(s[i]) : "f"(ga[i]));
            asm volatile("mov.b32 %0, %1;" : "=f"(o[i]) : "f"(gb[i]));
          }
        }
        mbar_arrive_cl(rempty, GE + (ps == 2 ? 24 : 8));
        if (ps == 2) break;
      }
      const uint32_t qw = base + wg * 8192, qt = QT >> (16 * ps), at = ps ? AT1 : AT0;
      {
        const uint32_t wt = ps ? WT1 : WT0;
        const uint64_t da0 = make_desc(qw + unit_of(qt, 2), 16, 1024), da1 = make_desc(qw + unit_of(qt, 3), 16, 1024);
        const uint64_t db0 = make_desc(base + unit_of(wt, 2), 8192, 1024), db1 = make_desc(base + unit_of(wt, 3), 8192, 1024);
        mbar_wait(gfull + 16, 1);
        bar_sync(2 + wg, 256);
        wg_fence();
#pragma unroll
        for (int kk = 0; kk < 4; kk++) mma_ss<1>(s, da0 + kk * 2, db0 + kk * 128, 1);
        wg_commit();
        mbar_wait(xfull + 24, 1);
        mbar_wait(gfull + 24, 1);
        wg_fence();
#pragma unroll
        for (int kk = 0; kk < 4; kk++) mma_ss<1>(s, da1 + kk * 2, db1 + kk * 128, 1);
        wg_commit();
        bar_arrive(3 - wg, 256);
        mbar_wait(ps == 0 ? bar_pread : bar_ofree + 8, 0);
        mbar_wait(bfull, 0);
        wg_wait<0>();
        keep(s);
        PROF(2, tid == 0, 8 + ps * 8);
        store_chunk<0>(s, qw + unit_of(qt, 0) + frag_offset(warp));
        store_chunk<1>(s, qw + unit_of(qt, 1) + frag_offset(warp));
        fence_async_smem();
        bar_sync(2 + wg, 256);
        wg_fence();
        issue_qk(s, qw + unit_of(qt, 0), qw + unit_of(qt, 1), base + unit_of(at, 0));
        wg_commit();
#pragma unroll
        for (int kk = 0; kk < 8; kk++) mma_ss<1>(o, (kk < 4 ? da0 : da1) + (kk & 3) * 2, (kk < 4 ? db0 : db1) + UNIT / 16 + (kk & 3) * 128, 1);
        wg_commit();
        bar_arrive(3 - wg, 256);
        wg_wait<1>();
        keep(s);
        mbar_arrive_cl(rempty, 0);
      }
      PROF(4, tid == 0 && ps == 1, 61);
      float l0 = 0.25f, l1 = 0.25f;
      auto step = [&](auto odd_c, const int j, uint32_t (&pw)[32], uint32_t (&pr)[32]) {
        constexpr bool ODD = decltype(odd_c)::value;
        const bool first = !ODD && (j & 2) == 0, last = ODD && j == 7;
        const uint32_t ph = (j >> 1) & 1;
        float i0, i1, a0, a1;
        if (first) { i0 = inv_quad_sum(l0); i1 = inv_quad_sum(l1); l0 = 0.f; l1 = 0.f; }
        bool redo = !ODD && (j | ps) == 0, again = false;
        while (true) {
          if (redo) {
            float m0 = fmaxf(s[0], s[1]), m1 = fmaxf(s[2], s[3]);
#pragma unroll
            for (int i = 1; i < 16; i++) { m0 = fmaxf(m0, fmaxf(s[4 * i], s[4 * i + 1])); m1 = fmaxf(m1, fmaxf(s[4 * i + 2], s[4 * i + 3])); }
            m0 = fmaxf(m0, __shfl_xor_sync(0xffffffffu, m0, 1)); m1 = fmaxf(m1, __shfl_xor_sync(0xffffffffu, m1, 1));
            m0 = fmaxf(m0, __shfl_xor_sync(0xffffffffu, m0, 2)); m1 = fmaxf(m1, __shfl_xor_sync(0xffffffffu, m1, 2));
            m0 *= SCL2; m1 *= SCL2;
            if (!first) {
              m0 = fmaxf(m0, f0); m1 = fmaxf(m1, f1);
              const float c0 = ex2(f0 - m0), c1 = ex2(f1 - m1);
              l0 *= c0; l1 *= c1;
              wg_wait<0>();
              keep(o);
#pragma unroll
              for (int i = 0; i < 16; i++) { o[4 * i] *= c0; o[4 * i + 1] *= c0; o[4 * i + 2] *= c1; o[4 * i + 3] *= c1; }
            }
            f0 = m0; f1 = m1;
          }
          float b0 = 0.f, b1 = 0.f;
          a0 = 0.f; a1 = 0.f;
#pragma unroll
          for (int i = 0; i < 16; i++) {
            const float e0 = ex2(fmaf(s[4 * i], SCL2, -f0)), e1 = ex2(fmaf(s[4 * i + 1], SCL2, -f0));
            const float e2 = ex2(fmaf(s[4 * i + 2], SCL2, -f1)), e3 = ex2(fmaf(s[4 * i + 3], SCL2, -f1));
            a0 += e0; b0 += e1; a1 += e2; b1 += e3;
            pw[2 * i] = pack_bf(e0, e1); pw[2 * i + 1] = pack_bf(e2, e3);
            if (i == VREL) {
#pragma unroll
              for (int k = 0; k < 2 * VREL + 2; k++) asm volatile("" : "+r"(pw[k])::"memory");
              mbar_wait(bar_mod, 0);
              wg_wait<0>();
              mbar_arrive_cl(rempty, ODD ? 16 : (j ? 0 : GE + 16), !again);
              if (!ODD) mbar_arrive_cl(rempty, GE + 24, !again && j == 0);
#pragma unroll
              for (int k = 4 * VREL + 4; k < 64; k++) asm volatile("" : "+f"(s[k])::"memory");
            }
          }
          a0 += b0; a1 += b1;
          if (redo) break;
          redo = __any_sync(0xffffffffu, !(a0 + a1 < 0x1p70f));
          if (first) {
            uint32_t m0 = __ballot_sync(0xffffffffu, a0 > 0x1p-50f), m1 = __ballot_sync(0xffffffffu, a1 > 0x1p-50f);
            m0 |= m0 >> 1; m1 |= m1 >> 1; m0 |= m0 >> 2; m1 |= m1 >> 2;
            redo = redo || (m0 & m1 & 0x11111111u) != 0x11111111u;
          }
          if (!redo) break;
          again = true;
        }
        l0 += a0; l1 += a1;
        keep(pw);
        keep(o);
        const uint32_t qo = qt >> (j ? 0 : 8);
        if (first) store_chunk<0>(o, i0, i1, qw + unit_of(qo, 0) + frag_offset(warp));
        keep(o);
        mbar_wait(bfull + (ODD ? 24 : 8), ph);
        bar_sync(2 + wg, 256);
        if (!last) {
          const uint32_t qn = qt >> (j >= 3 ? 8 : 0);
          wg_fence();
          issue_qk(s, qw + unit_of(qn, 0), qw + unit_of(qn, 1), base + unit_of(at, ODD ? 3 : 1));
          wg_commit();
          mbar_wait(bfull + (ODD ? 0 : 16), ODD ? ph ^ 1 : ph);
        }
        if (first) { store_chunk<1>(o, i0, i1, qw + unit_of(qo, 1) + frag_offset(warp)); keep(o); }
        wg_fence();
        issue_pv(o, pw, base + unit_of(at, ODD ? (last ? 3 : 0) : 2), !first);
        wg_commit();
        bar_arrive(3 - wg, 256);
        wg_wait<1>();
        keep(s);
        mbar_arrive_cl(rempty, ODD ? 24 : 8, !last);
        if (first) { fence_async_smem(); mbar_arrive_pred(bar_ofull + wg * 8, j); }
        PROF(4, tid == 0 && ps == 1, 51 + j);
      };
      uint32_t pa[32], pb[32];
#pragma unroll 1
      for (int j = 0; j < 8; j += 2) {
        step(std::false_type{}, j, pa, pb);
        step(std::true_type{}, j + 1, pb, pa);
      }
      {
        const float i0 = inv_quad_sum(l0), i1 = inv_quad_sum(l1);
        wg_wait<0>();
        keep(o);
        mbar_arrive_cl(rempty, 24);
        store_chunk<0>(o, i0, i1, qw + unit_of(qt, 2) + frag_offset(warp));
        store_chunk<1>(o, i0, i1, qw + unit_of(qt, 3) + frag_offset(warp));
        fence_async_smem();
        mbar_arrive(bar_ofull + 16 + wg * 8);
      }
      PROF(2, tid == 0, 10 + ps * 8);
    }

    const int ln = fresh_lane(), g = ln >> 2, tq = ln & 3, ct = warp * 32 + ln;
    const bool lane0 = ln == 0;
    const int lrow0 = warp * 16 + g;
    const int grow0 = rb * 128 + lrow0;
    const uint32_t res = base + OFF_RES, trow = res + wg * 8192 + frag_offset(warp);
    uint32_t xr[32];
    uint4 sv[4], own;
    uint32_t* sp[4];
#pragma unroll
    for (int k = 0; k < 4; k++) sp[k] = g_stats + ((((tq >> 1) * 4 + k) ^ cj) * SEQ + grow0 + (tq & 1) * 8) * 4;
    {
      const uint64_t da = make_desc(base + wg * 8192, 16, 1024), db = make_desc(base, 8192, 1024);
      constexpr int U = UNIT / 16;
#define HALF_STAGE(acc, xu, wu) _Pragma("unroll") for (int kk = 0; kk < 4; kk++) mma_ss<1>(acc, da + (xu) * U + kk * 2, db + (wu) * U + kk * 128, 1)
      PROF(10, ct == PT, 19); STAMP(0);
      cluster_arrive();
      mbar_wait(gfull, 1);
      mbar_wait(gfull + 8, 1);
      bar_sync(2 + wg, 256);
      wg_fence();
      HALF_STAGE(o, 7, 1);
      HALF_STAGE(o, 8, 3);
      wg_commit();
      STAMP(16);
      mbar_wait(gfull + 16, 1);
      STAMP(17);
      wg_fence();
      HALF_STAGE(o, 6, 11);
      wg_commit();
      bar_arrive(3 - wg, 256);
      mbar_wait(bar_par, 0);
      uint32_t* xo = g_xch + ((size_t)b * 8 * 256 + ct) * 4;
      const uint32_t* xi = g_xch + ((size_t)(b ^ 2) * 8 * 256 + ct) * 4;
      const uint32_t par1 = (~lds1(par + PAR_CONST + 4) & 1) << 16;
      uint32_t ga[16];
      uint4 bw[8];
#define LOAD_PAR _Pragma("unroll") for (int i = 0; i < 8; i++) {                                                               \
        ga[2 * i] = lds1(par + PAR_T2 + i * 128 + tq * 16 + 12); ga[2 * i + 1] = lds1(par + PAR_T2 + i * 128 + 64 + tq * 16 + 12); \
        bw[i] = lds4(par + PAR_T1 + i * 64 + tq * 16);                                                                          \
        if (!(g & 1)) { bw[i].x = 0x3f803f80u; bw[i].y = 0x3f803f80u; }                                                         \
      }
      if (PPOS == 0) LOAD_PAR
      wg_wait<1>();
      mbar_arrive_pred(bar_rel, lane0);
      wg_wait<0>();
      keep(o);
      mbar_arrive_pred(bar_ring, lane0);
      PROF(8, ct == PT, 20); STAMP(1);
#define SEND(i) st_b128(xo + (i) * 1024, (pack_bf(o[8 * (i)], o[8 * (i) + 1]) & ~0x10000u) | par1, pack_bf(o[8 * (i) + 2], o[8 * (i) + 3]), \
                        pack_bf(o[8 * (i) + 4], o[8 * (i) + 5]), pack_bf(o[8 * (i) + 6], o[8 * (i) + 7]))
#pragma unroll
      for (int i = 0; i < NS1; i++) SEND(i);
      PROF(8, ct == PT, 21); STAMP(2);
      bar_sync(2 + wg, 256);
      wg_fence();
      HALF_STAGE(s, 7, 0);
      HALF_STAGE(s, 8, 2);
      HALF_STAGE(s, 6, 10);
      wg_commit();
      bar_arrive(3 - wg, 256);
      STAMP(18);
      mbar_wait(gfull + 24, 1);
#pragma unroll
      for (int i = NS1; i < 8; i++) SEND(i);
      uint4 v[8];
#pragma unroll
      for (int i = 0; i < 4; i++) v[i] = ld_b128(xi + i * 1024);
      if (PPOS == 1) LOAD_PAR
      STAMP(19);
      mbar_wait(bar_xres, 0);
      wg_wait<0>();
      mbar_arrive_pred(bar_ring + 8, lane0);
      bar_sync(2 + wg, 256);
      STAMP(20);
#pragma unroll
      for (int i = 4; i < 8; i++) v[i] = ld_b128(xi + i * 1024);
      mbar_wait(bar_xres, 0);
      wg_fence();
      HALF_STAGE(s, 9, 4);
      wg_commit();
      mbar_wait(bar_rx, 0);
      wg_fence();
      HALF_STAGE(s, 1, 5);
      wg_commit();
      bar_arrive(3 - wg, 256);
      STAMP(21);
      wg_wait<0>();
      keep(s);
      mbar_arrive_pred(bar_ring + 16, lane0);
      PROF(10, ct == PT, 23); STAMP(4);
#pragma unroll
      for (int i = 0; i < 16; i += 2) ldmatrix4((trow ^ ((i & 7) << 4)) + (i >> 3) * 16384, xr[2 * i], xr[2 * i + 1], xr[2 * i + 2], xr[2 * i + 3]);
      if (PPOS == 2) LOAD_PAR
      uint32_t pk[32];
      pack_p(s, pk);
      keep(pk);
      {
        uint32_t n = 0;
        bool ok;
        do {
          ok = true;
#pragma unroll
          for (int i = 0; i < 8; i++)
            if ((v[i].x & 0x10000u) != par1) { v[i] = ld_b128(xi + i * 1024); ok = false; }
          watchdog(n);
        } while (!ok);
      }
      __syncwarp();
      PROF(8, ct == PT, 22); STAMP(3);
#pragma unroll
      for (int k = 0; k < 4; k++) sv[k] = ESV ? ld_b128(sp[k]) : make_uint4(0, 0, 0, 0);
      float ds[4] = {0.f, 0.f, 0.f, 0.f}, dl[4] = {0.f, 0.f, 0.f, 0.f}, q0[4] = {0.f, 0.f, 0.f, 0.f}, q1[4] = {0.f, 0.f, 0.f, 0.f};
#pragma unroll
      for (int i = 0; i < 8; i++) {
        const uint32_t u0 = hfma2(ga[2 * i], hadd2(pk[4 * i], v[i].x & ~0x10000u), xr[4 * i]);
        const uint32_t u1 = hfma2(ga[2 * i], hadd2(pk[4 * i + 1], v[i].y), xr[4 * i + 1]);
        const uint32_t u2 = hfma2(ga[2 * i + 1], hadd2(pk[4 * i + 2], v[i].z), xr[4 * i + 2]);
        const uint32_t u3 = hfma2(ga[2 * i + 1], hadd2(pk[4 * i + 3], v[i].w), xr[4 * i + 3]);
        xr[4 * i] = u0; xr[4 * i + 1] = u1; xr[4 * i + 2] = u2; xr[4 * i + 3] = u3;
        mma16816(ds, u0, u1, u2, u3, bw[i].x, bw[i].y);
        mma16816(dl, u0, u1, u2, u3, bw[i].z, bw[i].w);
        mma16816(q0, u0, u1, u2, u3, u0, u2);
        mma16816(q1, u0, u1, u2, u3, u1, u3);
      }
      const float sqa = __shfl_sync(0xffffffffu, (g & 1) ? q0[1] : q0[0], g * 4 + (g >> 1));
      const float sqb = __shfl_sync(0xffffffffu, (g & 1) ? q1[3] : q1[2], g * 4 + (g >> 1));
      own = (tq & 1) ? make_uint4(__float_as_uint(ds[2]), __float_as_uint(sqb), __float_as_uint(ds[3] + dl[3]), tag)
                                 : make_uint4(__float_as_uint(ds[0]), __float_as_uint(sqa), __float_as_uint(ds[1] + dl[1]), tag);
      if (tq < 2) st_b128(sp[0], own.x, own.y, own.z, own.w);
    }
    PROF(8, ct == PT, 29); STAMP(5);
    uint32_t mm, ih, il;
    float rbest;
    uint32_t wf[128];
    const uint32_t frow = (ln & 7) + (ln >> 4) * 8;
    const uint32_t wfo = base + (warp & 1) * 8192 + frow * 64 + ((((ln >> 3) & 1) ^ ((frow >> 1) & 3)) << 4);
#define LOAD_WF(m) _Pragma("unroll") for (int f = 0; f < 16; f++) {                                                   \
      const int r = ((f >> 1) * 4 + (m) * 2 + (f & 1)) * 4;                                                           \
      ldmatrix4t(((wfo + unit_of((m) ? FT_U : FT_G, warp >> 1)) ^ ((f & 1) * 32)) + (f >> 1) * 1024, wf[r], wf[r + 1], wf[r + 2], wf[r + 3]); \
    }
    bool early, wait1;
    {
#pragma unroll
      for (int i = 0; i < 16; i += 2) stmatrix4((trow ^ ((i & 7) << 4)) + (i >> 3) * 16384, xr[2 * i], xr[2 * i + 1], xr[2 * i + 2], xr[2 * i + 3]);
      const uint4 cst = lds4(par + PAR_CONST);
      const float A1 = __uint_as_float(cst.x), A2 = __uint_as_float(cst.z);
      uint32_t n = 0;
      early = false; wait1 = false;
#pragma unroll 1
      while (true) {
        uint32_t miss;
        asm volatile("{ .reg .pred p0, p1, p2, p3; .reg .b64 u, v; .reg .b128 w;\n"
                     "setp.ge.u32 p0, %22, 2; setp.ne.and.u32 p0, %4, %21, p0; setp.ne.u32 p1, %8, %21; setp.ne.u32 p2, %12, %21; setp.ne.u32 p3, %16, %21;\n"
                     "@p0 ld.relaxed.gpu.global.v4.u32 {%1, %2, %3, %4}, [%17];\n"
                     "@p1 ld.relaxed.gpu.global.v4.u32 {%5, %6, %7, %8}, [%18];\n"
                     "@p2 ld.relaxed.gpu.global.v4.u32 {%9, %10, %11, %12}, [%19];\n"
                     "@p3 ld.relaxed.gpu.global.v4.u32 {%13, %14, %15, %16}, [%20];\n"
                     "or.pred p0, p0, p1; or.pred p2, p2, p3; or.pred p0, p0, p2; vote.sync.any.pred p0, p0, 0xffffffff; selp.u32 %0, 1, 0, p0; }"
                     : "=r"(miss), "+r"(sv[0].x), "+r"(sv[0].y), "+r"(sv[0].z), "+r"(sv[0].w), "+r"(sv[1].x), "+r"(sv[1].y), "+r"(sv[1].z), "+r"(sv[1].w),
                       "+r"(sv[2].x), "+r"(sv[2].y), "+r"(sv[2].z), "+r"(sv[2].w), "+r"(sv[3].x), "+r"(sv[3].y), "+r"(sv[3].z), "+r"(sv[3].w)
                     : "l"(sp[0]), "l"(sp[1]), "l"(sp[2]), "l"(sp[3]), "r"(tag), "r"(tq) : "memory");
        if (!miss) break;
        wait1 = true;
        if (!early && (b >= NFFN || __all_sync(0xffffffffu, mbar_test(bar_box + (warp >> 1) * 8, 0)))) {
          early = true;
          LOAD_WF(0);
          __syncwarp();
          mbar_arrive_pred(bar_gate, lane0);
        }
        watchdog(n);
      }
      const uint4 v0 = tq < 2 ? own : sv[0], v1 = sv[1], v2 = sv[2], v3 = sv[3];
      PROF(8, ct == PT, 30); STAMP(6);
      float su = (__uint_as_float(v0.x) + __uint_as_float(v1.x)) + (__uint_as_float(v2.x) + __uint_as_float(v3.x));
      float sq = (__uint_as_float(v0.y) + __uint_as_float(v1.y)) + (__uint_as_float(v2.y) + __uint_as_float(v3.y));
      float dt = (__uint_as_float(v0.z) + __uint_as_float(v1.z)) + (__uint_as_float(v2.z) + __uint_as_float(v3.z));
      su += __shfl_xor_sync(0xffffffffu, su, 2); sq += __shfl_xor_sync(0xffffffffu, sq, 2); dt += __shfl_xor_sync(0xffffffffu, dt, 2);
      const float m = su * (1.f / DM);
      float mb, sd;
      ln_scalars(m, fmaxf(sq * (1.f / DM) - m * m, 0.f), mb, sd);
      const float inv = rcp(sd);
      rbest = (dt - mb * A1) * inv + A2;
      mm = pack_bf(mb, mb);
      ih = pack_bf(inv, inv);
      const float lo = inv - bf_lo(ih);
      il = pack_bf(lo, lo);
    }
    int ibest;
    {
      const uint32_t bits = __float_as_uint(rbest);
      const uint32_t key = (((int)bits < 0 ? ~bits : bits | 0x80000000u) & ~0x1ffu) | ((127 - lrow0 - (tq & 1) * 8) << 2) | tag;
      sts1(par + PAR_RED + warp * 4, __reduce_max_sync(0xffffffffu, key));
      PROF(8, ct == PT, 38); STAMP(7);
      uint32_t waited;
      asm volatile("{ .reg .pred p, q; setp.ne.u32 p, %1, 0; barrier.cta.red.or.pred q, 1, 256, p; selp.u32 %0, 1, 0, q; }" : "=r"(waited) : "r"((uint32_t)(wait1 && (wg || CW0))) : "memory");
      const uint4 ka = lds4(par + PAR_RED), kb = lds4(par + PAR_RED + 16);
      const uint32_t k2 = max(max(max(ka.x, ka.y), max(ka.z, ka.w)), max(max(kb.x, kb.y), max(kb.z, kb.w)));
      if (ct == 0 && ((cj & CWM) == 0 || (CWL && !waited))) st_relaxed(g_cand + rb, k2);
      ibest = 127 - ((k2 >> 2) & 127);
    }
    PROF(8, ct == PT, 39); STAMP(8);
    if ((ibest >> 4) == warp) {
      const int src = (ibest & 7) * 4 + ((ibest >> 3) & 1), ch = g * 2;
      const uint32_t cm = __shfl_sync(0xffffffffu, mm, src), ch_ = __shfl_sync(0xffffffffu, ih, src), cl = __shfl_sync(0xffffffffu, il, src);
      const uint32_t xa = res + (ch >> 3) * 16384 + ibest * 128 + (((ch & 7) ^ (ibest & 7)) << 4) + tq * 4;
      const uint32_t x0 = lds1(xa), x1 = lds1(xa ^ 16);
      const uint2 p0 = lds2(par + PAR_T2 + ch * 64 + tq * 16), p1 = lds2(par + PAR_T2 + ch * 64 + 64 + tq * 16);
      uint32_t* dst = g_row + rb * 2 * DM + cj * 128 + ln * 4;
      st_pairs(dst, ln_mod(x0, cm, ch_, cl, p0.x, p0.y), ln_mod(x1, cm, ch_, cl, p1.x, p1.y), tag);
      st_pairs(dst + DM, x0, x1, tag);
      __syncwarp();
    }
    PROF(8, ct == PT, 37); STAMP(9);
    uint32_t wd[64];
    const uint32_t wda = base + unit_of(FT_D, warp >> 1) + (warp & 1) * 8192 + frow * 128 + ((((ln >> 3) & 1) ^ (ln & 7)) << 4);
#define LOAD_WD(f) ldmatrix4t((wda ^ ((((f) >> 1) & 3) * 32)) + ((f) >> 3) * 4096 + ((f) & 1) * 2048, wd[4 * (f)], wd[4 * (f) + 1], wd[4 * (f) + 2], wd[4 * (f) + 3])
    if (!early) {
      if (b < NFFN) mbar_wait(bar_box + (warp >> 1) * 8, 0);
      LOAD_WF(0);
      __syncwarp();
      mbar_arrive_pred(bar_gate, lane0);
    }
    if (b < NFFN) {
      const uint32_t own = base + unit_of(FT_G, warp >> 1) + (warp & 1) * 8192;
      mbar_wait(bar_box + (4 + (warp >> 1)) * 8, 0);
      LOAD_WF(1);
      uint32_t* const ydst = g_ypart + ((size_t)(warp * 16 + tq * 2) * NFFN + b) * 8 + g;
      PROF(8, ct == PT, 31); STAMP(10);
      mbar_wait(bar_box + (8 + (warp >> 1)) * 8, 0);
#pragma unroll
      for (int f = 0; f < WDE; f++) LOAD_WD(f);
      STAMP(11);
      mbar_wait(bar_sel, 0);
      PROF(8, ct == PT, 33); STAMP(12);
      float d[8][4];
#pragma unroll
      for (int i = 0; i < 4; i++) { d[i][0] = 0.f; d[i][1] = 0.f; d[i][2] = 0.f; d[i][3] = 0.f; }
#pragma unroll
      for (int ks = 0; ks < 8; ks++) {
        const uint2 hb = lds2(own + 256 + ks * 32 + tq * 8);
#pragma unroll
        for (int mt = 0; mt < 4; mt++) {
          const int r = ks * 16 + mt * 4;
          mma16816(d[mt], wf[r], wf[r + 1], wf[r + 2], wf[r + 3], hb.x, hb.y);
        }
      }
      sts2(own + (tq * 8 + g) * 8, __float_as_uint((tq & 2) ? ((tq & 1) ? d[1][2] : d[1][0]) : ((tq & 1) ? d[0][2] : d[0][0])),
           __float_as_uint((tq & 2) ? ((tq & 1) ? d[3][2] : d[3][0]) : ((tq & 1) ? d[2][2] : d[2][0])));
      bar_sync(1, 256);
      uint32_t ab[4];
      {
        float G = 0.f, U = 0.f;
        uint2 pv[8];
#pragma unroll
        for (int w8 = 0; w8 < 8; w8++) pv[w8] = lds2(base + ln * 8 + ((FT_G >> (w8 >> 1) * 4) & 15) * UNIT + (w8 & 1) * 8192);
#pragma unroll
        for (int w8 = 0; w8 < 8; w8 += 2) {
          G += __uint_as_float(pv[w8].x) + __uint_as_float(pv[w8 + 1].x);
          U += __uint_as_float(pv[w8].y) + __uint_as_float(pv[w8 + 1].y);
        }
#pragma unroll
        for (int f = WDE; f < 16; f++) LOAD_WD(f);
        const float act = rbf(silu_f(rbf(G))) * rbf(U);
        const uint32_t pk = pack_bf(act, __shfl_down_sync(0xffffffffu, act, 1));
#pragma unroll
        for (int i = 0; i < 4; i++) ab[i] = __shfl_sync(0xffffffffu, pk, i * 8 + tq * 2);
      }
      PROF(8, ct == PT, 34); STAMP(13);
#pragma unroll
      for (int mt = 0; mt < 8; mt++) {
        d[mt][0] = 0.f; d[mt][1] = 0.f; d[mt][2] = 0.f; d[mt][3] = 0.f;
        mma16816(d[mt], wd[mt * 8], wd[mt * 8 + 1], wd[mt * 8 + 2], wd[mt * 8 + 3], ab[0], ab[1]);
        mma16816(d[mt], wd[mt * 8 + 4], wd[mt * 8 + 5], wd[mt * 8 + 6], wd[mt * 8 + 7], ab[2], ab[3]);
      }
#pragma unroll
      for (int i = 0; i < 4; i++) {
        const int m4 = (i >> 1) * 4, e = (i & 1) * 2;
        const float y = (tq & 2) ? ((tq & 1) ? d[m4 + 3][e] : d[m4 + 2][e]) : ((tq & 1) ? d[m4 + 1][e] : d[m4][e]);
        st_relaxed(ydst + (m4 * 2 + (i & 1)) * NFFN * 8, tagf(y, tag));
      }
      PROF(8, ct == PT, 35); STAMP(14);
    }
    mbar_wait(bar_sel, 0);
    mbar_arrive_pred(bar_win, ct == 0);
    const int iwin = lds1(par + PAR_CONST + 60) & 0x7ff;
    {
      const uint32_t mm0 = __shfl_sync(0xffffffffu, mm, ln & ~1), mm1 = __shfl_sync(0xffffffffu, mm, ln | 1);
      const uint32_t ih0 = __shfl_sync(0xffffffffu, ih, ln & ~1), ih1 = __shfl_sync(0xffffffffu, ih, ln | 1);
      const uint32_t il0 = __shfl_sync(0xffffffffu, il, ln & ~1), il1 = __shfl_sync(0xffffffffu, il, ln | 1);
      const bool mine = (iwin >> 4) == rb * 8 + warp;
#pragma unroll 1
      for (int hf = 0; hf < 2; hf++) {
        uint32_t x[16];
#pragma unroll
        for (int i = 0; i < 8; i += 2) ldmatrix4((trow ^ (i << 4)) + hf * 16384, x[2 * i], x[2 * i + 1], x[2 * i + 2], x[2 * i + 3]);
#pragma unroll
        for (int i = 0; i < 8; i++) {
          const uint4 pv = lds4(par + PAR_T2 + (hf * 8 + i) * 64 + tq * 16);
          x[2 * i] = hadd2(x[2 * i], hmul2(pv.z, ln_mod(x[2 * i], mm0, ih0, il0, pv.x, pv.y)));
          x[2 * i + 1] = hadd2(x[2 * i + 1], hmul2(pv.z, ln_mod(x[2 * i + 1], mm1, ih1, il1, pv.x, pv.y)));
        }
        if (mine) {
          uint32_t* dst = reinterpret_cast<uint32_t*>(P.out + (size_t)grow0 * DM + cj * 128 + hf * 64) + tq;
#pragma unroll
          for (int i = 0; i < 8; i++) {
            if (grow0 != iwin) dst[i * 4] = x[2 * i];
            if (grow0 + 8 != iwin) dst[i * 4 + 4 * DM] = x[2 * i + 1];
          }
        } else {
#pragma unroll
          for (int i = 0; i < 8; i += 2) stmatrix4((trow ^ (i << 4)) + hf * 16384, x[2 * i], x[2 * i + 1], x[2 * i + 2], x[2 * i + 3]);
          fence_async_smem();
          __syncwarp();
          if (elect_one()) {
            tma2d_store(&maps.out, res + hf * 16384 + warp * 2048, cj * 128 + hf * 64, rb * 128 + warp * 16);
            asm volatile("cp.async.bulk.commit_group;" ::: "memory");
          }
        }
      }
      asm volatile("cp.async.bulk.wait_group.read 0;" ::: "memory");
    }
    PROF(8, ct == PT, 11); STAMP(15);
    cluster_wait();
  }
}

typedef CUresult (*EncodeFn)(CUtensorMap*, CUtensorMapDataType, cuuint32_t, void*, const cuuint64_t*, const cuuint64_t*,
                             const cuuint32_t*, const cuuint32_t*, CUtensorMapInterleave, CUtensorMapSwizzle,
                             CUtensorMapL2promotion, CUtensorMapFloatOOBfill);

void map2d(EncodeFn enc, CUtensorMap* m, const void* p, uint64_t rows, uint64_t cols, uint32_t brows) {
  cuuint64_t dims[2] = {cols, rows}, strides[1] = {cols * 2};
  cuuint32_t box[2] = {64, brows}, es[2] = {1, 1};
  enc(m, CU_TENSOR_MAP_DATA_TYPE_BFLOAT16, 2, const_cast<void*>(p), dims, strides, box, es, CU_TENSOR_MAP_INTERLEAVE_NONE,
      CU_TENSOR_MAP_SWIZZLE_128B, CU_TENSOR_MAP_L2_PROMOTION_L2_256B, CU_TENSOR_MAP_FLOAT_OOB_FILL_NONE);
}
void map2d_narrow(EncodeFn enc, CUtensorMap* m, const void* p, uint64_t rows, uint64_t cols, uint32_t brows) {
  cuuint64_t dims[2] = {cols, rows}, strides[1] = {cols * 2};
  cuuint32_t box[2] = {32, brows}, es[2] = {1, 1};
  enc(m, CU_TENSOR_MAP_DATA_TYPE_BFLOAT16, 2, const_cast<void*>(p), dims, strides, box, es, CU_TENSOR_MAP_INTERLEAVE_NONE,
      CU_TENSOR_MAP_SWIZZLE_64B, CU_TENSOR_MAP_L2_PROMOTION_L2_64B, CU_TENSOR_MAP_FLOAT_OOB_FILL_NONE);
}
void map3d(EncodeFn enc, CUtensorMap* m, const void* p, uint64_t rows, uint64_t cols, uint32_t brows, uint32_t nch) {
  cuuint64_t dims[3] = {64, rows, cols / 64}, strides[2] = {cols * 2, 128};
  cuuint32_t box[3] = {64, brows, nch}, es[3] = {1, 1, 1};
  enc(m, CU_TENSOR_MAP_DATA_TYPE_BFLOAT16, 3, const_cast<void*>(p), dims, strides, box, es, CU_TENSOR_MAP_INTERLEAVE_NONE,
      CU_TENSOR_MAP_SWIZZLE_128B, CU_TENSOR_MAP_L2_PROMOTION_L2_256B, CU_TENSOR_MAP_FLOAT_OOB_FILL_NONE);
}

}

extern "C" void kernel_launch(void* const* d_in, const int* in_sizes, int n_in, void* d_out, int out_size) {
  (void)in_sizes; (void)n_in; (void)out_size;
  static EncodeFn enc = nullptr;
  if (!enc) {
    void* fn = nullptr;
    cudaDriverEntryPointQueryResult st;
    cudaGetDriverEntryPoint("cuTensorMapEncodeTiled", &fn, cudaEnableDefault, &st);
    enc = (EncodeFn)fn;
    cudaFuncSetAttribute(fused_kernel, cudaFuncAttributeMaxDynamicSharedMemorySize, SMEM_BYTES);
  }
  Maps maps;
  map2d(enc, &maps.x, d_in[0], SEQ, DM, 128);
  map2d(enc, &maps.out, d_out, SEQ, DM, 16);
  map3d(enc, &maps.wq, d_in[3], DM, NQ, 64, 2);
  map3d(enc, &maps.k, d_in[1], 4 * SK, 128, 128, 1);
  map3d(enc, &maps.v, d_in[2], 4 * SK, 128, 128, 1);
  map3d(enc, &maps.wo, d_in[4], NQ, DM, 64, 2);
  map2d_narrow(enc, &maps.wg, d_in[7], DM, FF, 256);
  map2d_narrow(enc, &maps.wu, d_in[8], DM, FF, 256);
  map3d(enc, &maps.wd, d_in[9], FF, DM, 32, 4);
  map2d_narrow(enc, &maps.wm, d_in[11], DM, NMOD, 256);
  Ptrs p;
  p.x = (const __nv_bfloat16*)d_in[0];
  p.w_r = (const __nv_bfloat16*)d_in[6];
  p.w_gate = (const __nv_bfloat16*)d_in[7];
  p.w_up = (const __nv_bfloat16*)d_in[8];
  p.w_down = (const __nv_bfloat16*)d_in[9];
  p.c = (const __nv_bfloat16*)d_in[10];
  p.w_mod = (const __nv_bfloat16*)d_in[11];
  p.out = (__nv_bfloat16*)d_out;
  fused_kernel<<<NMAIN + NHELP, 384, SMEM_BYTES>>>(maps, p);
}
```

```cpp
#include <cuda_runtime.h>
#include <cuda_bf16.h>
#include <cuda.h>
#include <stdint.h>
#include <type_traits>

#define HD 2
#define HDX 2
#define XF 4
#define XE 32
#define XR 0
#define NRS 8
#define FPACE 3
#define GOST 20
#define WB 3
#define WN 24
#define RES0 17
#define RES1 20
#define HU 32
#define NS1 6
#define PG0 0
#define PSL 0
#define CWM 7
#define WDE 16
#define CWL 1
#define CW0 0
#define ESV 1
#define PPOS 1
#define FB0 0
#define FB2 8
#define OPS 8192
#define OFL 0
#define ODS 8
#define PORD 0
#define VREL 7
#define E0 3

namespace {

constexpr int SEQ = 2048, DM = 1024, NQ = 4096, SK = 2048, WIN = 512, FF = 3584, NMOD = 6144;
constexpr int NMAIN = 128, NHELP = 4, NFFN = 112;
constexpr int NSLOT = 4, SLOT_BYTES = 32768, UNIT = 16384, GST_BYTES = 3 * UNIT;
constexpr uint32_t XT1 = 0xDCBA, XT2 = 0x9687;
constexpr uint32_t WT0 = 0xA741, WT1 = 0x7420, WT2 = 0x4A20;
constexpr uint32_t AT0 = WT1, AT1 = WT2;
constexpr uint32_t QT = 0xDC9696DC;
constexpr int OFF_STAGE = 12 * UNIT;
constexpr uint32_t FT_G = 0x07B3, FT_U = 0xA628, FT_D = 0x5149;
constexpr int OFF_RES = 12 * UNIT;
constexpr int OFF_PAR = 14 * UNIT;
constexpr int OFF_BAR = OFF_PAR + 2528;
constexpr int SMEM_BYTES = OFF_BAR + 544;
static_assert(SMEM_BYTES <= 232448, "smem");

constexpr int PAR_T1 = 0;
constexpr int PAR_T2 = 512;
constexpr int PAR_CONST = 1536;
constexpr int PAR_RED = 1600;
constexpr int PAR_SINK = 2176;

struct Maps {
  CUtensorMap x, wq, k, v, wo, wg, wu, wd, wm, out;
};
struct Ptrs {
  const __nv_bfloat16 *x, *w_r, *c, *w_mod, *w_gate, *w_up, *w_down;
  __nv_bfloat16* out;
};

__device__ __align__(1024) uint8_t g_act[16 * 80 * UNIT];
__device__ __align__(128) uint32_t g_mod[NMOD];
__device__ __align__(128) uint32_t g_modp[2 * 2 * DM];
__device__ __align__(128) uint32_t g_ln1[SEQ * 4];
__device__ __align__(128) uint32_t g_cnt_h[16 * 32];
__device__ __align__(128) uint32_t g_cnt_o[128 * 32];
__device__ __align__(128) uint32_t g_xch[NMAIN * 8 * 256 * 4];
__device__ __align__(128) uint32_t g_stats[8 * SEQ * 4];
__device__ __align__(128) uint32_t g_cand[32];
__device__ __align__(128) uint32_t g_row[16 * 2 * DM];
__device__ __align__(128) uint32_t g_ypart[NMAIN * NFFN * 8];
__device__ uint32_t g_epoch;

__device__ __forceinline__ uint32_t fresh_lane() { uint32_t l; asm volatile("mov.u32 %0, %%laneid;" : "=r"(l)); return l; }
__device__ __forceinline__ uint32_t frag_offset(int warp) {
  const uint32_t l = fresh_lane();
  return ((warp & 3) * 16 + (l & 15)) * 128 + (((l >> 4) ^ (l & 7)) << 4);
}
__device__ __forceinline__ bool elect_one() {
  uint32_t p;
  asm volatile("{ .reg .pred q; elect.sync _|q, 0xffffffff; selp.u32 %0, 1, 0, q; }" : "=r"(p));
  return p;
}
__device__ __forceinline__ uint32_t smem_u32(const void* p) { return (uint32_t)__cvta_generic_to_shared(p); }
__device__ __forceinline__ void mbar_init(uint32_t bar, uint32_t cnt) {
  asm volatile("mbarrier.init.shared::cta.b64 [%0], %1;" ::"r"(bar), "r"(cnt) : "memory");
}
__device__ __forceinline__ void mbar_expect_tx(uint32_t bar, uint32_t bytes) {
  asm volatile("mbarrier.arrive.expect_tx.shared::cta.b64 _, [%0], %1;" ::"r"(bar), "r"(bytes) : "memory");
}
__device__ __forceinline__ void mbar_arrive(uint32_t bar) {
  asm volatile("mbarrier.arrive.shared::cta.b64 _, [%0];" ::"r"(bar) : "memory");
}
__device__ __forceinline__ void mbar_arrive_pred(uint32_t bar, bool p) {
  asm volatile("{ .reg .pred p; setp.ne.b32 p, %1, 0; @p mbarrier.arrive.shared::cta.b64 _, [%0]; }" ::"r"(bar), "r"((int)p) : "memory");
}
__device__ __forceinline__ void mbar_arrive_cl(uint32_t bar, uint32_t off, bool p = true) {
  asm volatile("{ .reg .pred p, q; .reg .b32 a; setp.ne.b32 q, %2, 0; setp.ne.and.b32 p, %0, 0, q; add.u32 a, %0, %1; @p mbarrier.arrive.shared::cluster.b64 _, [a]; }"
               ::"r"(bar), "r"(off), "r"((int)p) : "memory");
}
__device__ __forceinline__ uint32_t mapa(uint32_t addr, uint32_t cta) {
  uint32_t r; asm("mapa.shared::cluster.u32 %0, %1, %2;" : "=r"(r) : "r"(addr), "r"(cta)); return r;
}
__device__ __forceinline__ void cluster_arrive() { asm volatile("barrier.cluster.arrive.relaxed.aligned;" ::: "memory"); }
__device__ __forceinline__ void cluster_wait() { asm volatile("barrier.cluster.wait.aligned;" ::: "memory"); }
__device__ __forceinline__ void watchdog(uint32_t& n) {
}
__device__ __forceinline__ void mbar_wait(uint32_t bar, uint32_t parity) {
  asm volatile("{\n.reg .pred p;\nWAIT_%=:\nmbarrier.try_wait.parity.shared::cta.b64 p, [%0], %1;\n@!p bra WAIT_%=;\n}" ::"r"(bar), "r"(parity) : "memory");
}
__device__ __forceinline__ bool mbar_test(uint32_t bar, uint32_t parity) {
  uint32_t ok;
  asm volatile("{\n.reg .pred p;\nmbarrier.test_wait.parity.shared::cta.b64 p, [%1], %2;\nselp.u32 %0, 1, 0, p;\n}" : "=r"(ok) : "r"(bar), "r"(parity) : "memory");
  return ok;
}
__device__ __forceinline__ uint64_t l2_stream() {
  uint64_t f; asm("createpolicy.fractional.L2::evict_first.b64 %0, 1.0;" : "=l"(f)); return f;
}
__device__ __forceinline__ void tma2d(uint32_t dst, const CUtensorMap* m, int c0, int c1, uint32_t bar) {
  asm volatile("cp.async.bulk.tensor.2d.shared::cluster.global.mbarrier::complete_tx::bytes.L2::cache_hint [%0], [%1, {%3, %4}], [%2], %5;"
               ::"r"(dst), "l"(m), "r"(bar), "r"(c0), "r"(c1), "l"(l2_stream()) : "memory");
}
__device__ __forceinline__ void bulk_load(uint32_t dst, const void* src, uint32_t bytes, uint32_t bar) {
  asm volatile("cp.async.bulk.shared::cluster.global.mbarrier::complete_tx::bytes [%0], [%1], %2, [%3];" ::"r"(dst), "l"(src), "r"(bytes), "r"(bar) : "memory");
}
__device__ __forceinline__ void bulk_load_stream(uint32_t dst, const void* src, uint32_t bytes, uint32_t bar) {
  asm volatile("cp.async.bulk.shared::cluster.global.mbarrier::complete_tx::bytes.L2::cache_hint [%0], [%1], %2, [%3], %4;"
               ::"r"(dst), "l"(src), "r"(bytes), "r"(bar), "l"(l2_stream()) : "memory");
}
__device__ __forceinline__ void tma2d_store(const CUtensorMap* m, uint32_t src, int c0, int c1) {
  asm volatile("cp.async.bulk.tensor.2d.global.shared::cta.bulk_group [%0, {%2, %3}], [%1];" ::"l"(m), "r"(src), "r"(c0), "r"(c1) : "memory");
}
__device__ __forceinline__ void bulk_store(void* dst, uint32_t src, uint32_t bytes) {
  asm volatile("cp.async.bulk.global.shared::cta.bulk_group [%0], [%1], %2;" ::"l"(dst), "r"(src), "r"(bytes) : "memory");
}
__device__ __forceinline__ uint32_t unit_of(uint32_t table, uint32_t i) { return ((table >> (i * 4)) & 15) * UNIT; }
__device__ __forceinline__ void tma3d(uint32_t dst, const CUtensorMap* m, int c0, int c1, int c2, uint32_t bar) {
  asm volatile("cp.async.bulk.tensor.3d.shared::cluster.global.mbarrier::complete_tx::bytes.L2::cache_hint [%0], [%1, {%3, %4, %5}], [%2], %6;"
               ::"r"(dst), "l"(m), "r"(bar), "r"(c0), "r"(c1), "r"(c2), "l"(l2_stream()) : "memory");
}
template <bool STREAM>
__device__ __forceinline__ void tma3d_mc(uint32_t dst, const CUtensorMap* m, int c0, int c1, int c2, uint32_t bar) {
  if (STREAM)
    asm volatile("cp.async.bulk.tensor.3d.shared::cluster.global.mbarrier::complete_tx::bytes.multicast::cluster.L2::cache_hint [%0], [%1, {%3, %4, %5}], [%2], %6, %7;"
                 ::"r"(dst), "l"(m), "r"(bar), "r"(c0), "r"(c1), "r"(c2), "h"((uint16_t)3), "l"(l2_stream()) : "memory");
  else
    asm volatile("cp.async.bulk.tensor.3d.shared::cluster.global.mbarrier::complete_tx::bytes.multicast::cluster [%0], [%1, {%3, %4, %5}], [%2], %6;"
                 ::"r"(dst), "l"(m), "r"(bar), "r"(c0), "r"(c1), "r"(c2), "h"((uint16_t)3) : "memory");
}
__device__ __forceinline__ void prefetch_map(const CUtensorMap* m) {
  asm volatile("prefetch.tensormap [%0];" ::"l"(m) : "memory");
}
__device__ __forceinline__ void fence_async() { asm volatile("fence.proxy.async.global;" ::: "memory"); }
__device__ __forceinline__ void fence_async_smem() { asm volatile("fence.proxy.async.shared::cta;" ::: "memory"); }
__device__ __forceinline__ void bar_sync(int id, int n) { asm volatile("bar.sync %0, %1;" ::"r"(id), "r"(n) : "memory"); }
__device__ __forceinline__ void bar_arrive(int id, int n) { asm volatile("bar.arrive %0, %1;" ::"r"(id), "r"(n) : "memory"); }
__device__ __forceinline__ void wg_fence() { asm volatile("wgmma.fence.sync.aligned;" ::: "memory"); }
__device__ __forceinline__ void wg_commit() { asm volatile("wgmma.commit_group.sync.aligned;" ::: "memory"); }
template <int N> __device__ __forceinline__ void wg_wait() { asm volatile("wgmma.wait_group.sync.aligned %0;" ::"n"(N) : "memory"); }
__device__ __forceinline__ uint64_t make_desc(uint32_t addr, uint32_t lbo, uint32_t sbo) {
  return (uint64_t)((addr & 0x3FFFF) >> 4) | ((uint64_t)(lbo >> 4) << 16) | ((uint64_t)(sbo >> 4) << 32) | (1ull << 62);
}
__device__ __forceinline__ uint32_t ld_relaxed(const uint32_t* p) {
  uint32_t v; asm volatile("ld.relaxed.gpu.global.u32 %0, [%1];" : "=r"(v) : "l"(p) : "memory"); return v;
}
__device__ __forceinline__ uint32_t ld_acquire(const uint32_t* p) {
  uint32_t v; asm volatile("ld.acquire.gpu.global.u32 %0, [%1];" : "=r"(v) : "l"(p) : "memory"); return v;
}
__device__ __forceinline__ uint4 ld_relaxed4(const uint32_t* p) {
  uint4 v; asm volatile("ld.relaxed.gpu.global.v4.u32 {%0,%1,%2,%3}, [%4];" : "=r"(v.x), "=r"(v.y), "=r"(v.z), "=r"(v.w) : "l"(p) : "memory"); return v;
}
__device__ __forceinline__ uint2 ld_relaxed2(const uint32_t* p) {
  uint2 v; asm volatile("ld.relaxed.gpu.global.v2.u32 {%0,%1}, [%2];" : "=r"(v.x), "=r"(v.y) : "l"(p) : "memory"); return v;
}
__device__ __forceinline__ void st_relaxed(uint32_t* p, uint32_t v) {
  asm volatile("st.relaxed.gpu.global.u32 [%0], %1;" ::"l"(p), "r"(v) : "memory");
}
__device__ __forceinline__ void st_relaxed2(uint32_t* p, uint32_t a, uint32_t b) {
  asm volatile("st.relaxed.gpu.global.v2.u32 [%0], {%1,%2};" ::"l"(p), "r"(a), "r"(b) : "memory");
}
__device__ __forceinline__ void st_relaxed4(uint32_t* p, uint32_t a, uint32_t b, uint32_t c, uint32_t d) {
  asm volatile("st.relaxed.gpu.global.v4.u32 [%0], {%1,%2,%3,%4};" ::"l"(p), "r"(a), "r"(b), "r"(c), "r"(d) : "memory");
}
__device__ __forceinline__ void st_b128(uint32_t* p, uint32_t a, uint32_t b, uint32_t c, uint32_t d) {
  asm volatile("{ .reg .b64 u, v; .reg .b128 w; mov.b64 u, {%1, %2}; mov.b64 v, {%3, %4}; mov.b128 w, {u, v}; st.relaxed.gpu.global.b128 [%0], w; }"
               ::"l"(p), "r"(a), "r"(b), "r"(c), "r"(d) : "memory");
}
__device__ __forceinline__ uint4 ld_b128(const uint32_t* p) {
  uint4 r;
  asm volatile("{ .reg .b64 u, v; .reg .b128 w; ld.relaxed.gpu.global.b128 w, [%4]; mov.b128 {u, v}, w; mov.b64 {%0, %1}, u; mov.b64 {%2, %3}, v; }"
               : "=r"(r.x), "=r"(r.y), "=r"(r.z), "=r"(r.w) : "l"(p) : "memory");
  return r;
}
__device__ __forceinline__ void st_pairs(uint32_t* p, uint32_t a, uint32_t b, uint32_t tag) {
  asm volatile("{ .reg .b64 u, v; mov.b64 u, {%1, %3}; mov.b64 v, {%2, %3}; st.relaxed.gpu.global.v2.b64 [%0], {u, v}; }"
               ::"l"(p), "r"(a), "r"(b), "r"(tag) : "memory");
}
__device__ __forceinline__ uint4 ld_pairs(const uint32_t* p) {
  uint4 v;
  asm volatile("{ .reg .b64 u, v; ld.relaxed.gpu.global.v2.b64 {u, v}, [%4]; mov.b64 {%0, %1}, u; mov.b64 {%2, %3}, v; }"
               : "=r"(v.x), "=r"(v.y), "=r"(v.z), "=r"(v.w) : "l"(p) : "memory");
  return v;
}
__device__ __forceinline__ uint2 ld_pair(const uint32_t* p) {
  uint2 v;
  asm volatile("{ .reg .b64 u; ld.relaxed.gpu.global.b64 u, [%2]; mov.b64 {%0, %1}, u; }" : "=r"(v.x), "=r"(v.y) : "l"(p) : "memory");
  return v;
}
__device__ __forceinline__ void red_release(uint32_t* p, uint32_t v) {
  asm volatile("red.release.gpu.global.add.u32 [%0], %1;" ::"l"(p), "r"(v) : "memory");
}
__device__ __forceinline__ uint32_t ldg_nc1(const void* p) {
  uint32_t v;
  asm volatile("ld.global.nc.u32 %0, [%1];" : "=r"(v) : "l"(p));
  return v;
}
__device__ __forceinline__ uint4 ldg_nc4(const void* p) {
  uint4 v; asm volatile("ld.global.nc.L1::no_allocate.v4.u32 {%0,%1,%2,%3}, [%4];" : "=r"(v.x), "=r"(v.y), "=r"(v.z), "=r"(v.w) : "l"(p)); return v;
}
__device__ __forceinline__ uint4 ldg_stream4(const void* p) {
  uint4 v;
  asm volatile("ld.global.nc.L1::no_allocate.L2::cache_hint.v4.u32 {%0,%1,%2,%3}, [%4], %5;" : "=r"(v.x), "=r"(v.y), "=r"(v.z), "=r"(v.w) : "l"(p), "l"(l2_stream()));
  return v;
}
__device__ __forceinline__ void stg4(void* p, uint4 v) {
  asm volatile("st.global.v4.u32 [%0], {%1,%2,%3,%4};" ::"l"(p), "r"(v.x), "r"(v.y), "r"(v.z), "r"(v.w) : "memory");
}
__device__ __forceinline__ void wait_counter(const uint32_t* p, uint32_t target) {
  uint32_t n = 0;
  while (__any_sync(0xffffffffu, (int)(ld_acquire(p) - target) < 0)) { watchdog(n); }
}
__device__ __forceinline__ uint32_t tagf(float v, uint32_t tag) { return (__float_as_uint(v) & ~3u) | tag; }
__device__ __forceinline__ bool tag_ok(uint4 v, uint32_t tag) { return (((v.x ^ tag) | (v.y ^ tag) | (v.z ^ tag) | (v.w ^ tag)) & 3u) == 0; }
__device__ __forceinline__ float untag_sum(uint32_t a, uint32_t b) { return __uint_as_float(a & ~3u) + __uint_as_float(b & ~3u); }
__device__ __forceinline__ uint4 poll4(const uint32_t* p, uint32_t tag) {
  uint4 v = ld_relaxed4(p);
  uint32_t n = 0;
  while (!__all_sync(0xffffffffu, tag_ok(v, tag))) { v = ld_relaxed4(p); watchdog(n); }
  return v;
}
__device__ __forceinline__ float bf_lo(uint32_t v) { return __uint_as_float(v << 16); }
__device__ __forceinline__ float bf_hi(uint32_t v) { return __uint_as_float(v & 0xffff0000u); }
__device__ __forceinline__ uint32_t pack_bf(float lo, float hi) {
  uint32_t r; asm("cvt.rn.bf16x2.f32 %0, %1, %2;" : "=r"(r) : "f"(hi), "f"(lo)); return r;
}
__device__ __forceinline__ float rbf(float v) { return __uint_as_float(pack_bf(0.f, v) & 0xffff0000u); }
__device__ __forceinline__ uint32_t hmul2(uint32_t a, uint32_t b) {
  uint32_t r; asm("mul.rn.bf16x2 %0, %1, %2;" : "=r"(r) : "r"(a), "r"(b)); return r;
}
__device__ __forceinline__ uint32_t hadd2(uint32_t a, uint32_t b) {
  uint32_t r; asm("add.rn.bf16x2 %0, %1, %2;" : "=r"(r) : "r"(a), "r"(b)); return r;
}
__device__ __forceinline__ uint32_t hsub2(uint32_t a, uint32_t b) {
  uint32_t r; asm("sub.rn.bf16x2 %0, %1, %2;" : "=r"(r) : "r"(a), "r"(b)); return r;
}
__device__ __forceinline__ uint32_t hmax2(uint32_t a, uint32_t b) {
  uint32_t r; asm("max.bf16x2 %0, %1, %2;" : "=r"(r) : "r"(a), "r"(b)); return r;
}
__device__ __forceinline__ float rcp(float x) { float r; asm("rcp.approx.ftz.f32 %0, %1;" : "=f"(r) : "f"(x)); return r; }
__device__ __forceinline__ float ex2(float x) { float r; asm("ex2.approx.ftz.f32 %0, %1;" : "=f"(r) : "f"(x)); return r; }
__device__ __forceinline__ void stmatrix4(uint32_t addr, uint32_t a, uint32_t b, uint32_t c, uint32_t d) {
  asm volatile("stmatrix.sync.aligned.m8n8.x4.shared.b16 [%0], {%1,%2,%3,%4};" ::"r"(addr), "r"(a), "r"(b), "r"(c), "r"(d) : "memory");
}
__device__ __forceinline__ void ldmatrix4(uint32_t addr, uint32_t& a, uint32_t& b, uint32_t& c, uint32_t& d) {
  asm volatile("ldmatrix.sync.aligned.m8n8.x4.shared.b16 {%0,%1,%2,%3}, [%4];" : "=r"(a), "=r"(b), "=r"(c), "=r"(d) : "r"(addr) : "memory");
}
__device__ __forceinline__ void ldmatrix4t(uint32_t addr, uint32_t& a, uint32_t& b, uint32_t& c, uint32_t& d) {
  asm volatile("ldmatrix.sync.aligned.m8n8.x4.trans.shared.b16 {%0,%1,%2,%3}, [%4];" : "=r"(a), "=r"(b), "=r"(c), "=r"(d) : "r"(addr) : "memory");
}
__device__ __forceinline__ void mma16816(float (&d)[4], uint32_t a0, uint32_t a1, uint32_t a2, uint32_t a3, uint32_t b0, uint32_t b1) {
  asm volatile("mma.sync.aligned.m16n8k16.row.col.f32.bf16.bf16.f32 {%0,%1,%2,%3}, {%4,%5,%6,%7}, {%8,%9}, {%0,%1,%2,%3};"
               : "+f"(d[0]), "+f"(d[1]), "+f"(d[2]), "+f"(d[3]) : "r"(a0), "r"(a1), "r"(a2), "r"(a3), "r"(b0), "r"(b1));
}
__device__ __forceinline__ void sts1(uint32_t a, uint32_t v) { asm volatile("st.shared.u32 [%0], %1;" ::"r"(a), "r"(v) : "memory"); }
__device__ __forceinline__ uint4 lds4(uint32_t a) {
  uint4 v; asm volatile("ld.shared.v4.u32 {%0,%1,%2,%3}, [%4];" : "=r"(v.x), "=r"(v.y), "=r"(v.z), "=r"(v.w) : "r"(a) : "memory"); return v;
}
__device__ __forceinline__ uint2 lds2(uint32_t a) {
  uint2 v; asm volatile("ld.shared.v2.u32 {%0,%1}, [%2];" : "=r"(v.x), "=r"(v.y) : "r"(a) : "memory"); return v;
}
__device__ __forceinline__ uint32_t lds1(uint32_t a) {
  uint32_t v; asm volatile("ld.shared.u32 %0, [%1];" : "=r"(v) : "r"(a) : "memory"); return v;
}
__device__ __forceinline__ void sts2(uint32_t a, uint32_t x, uint32_t y) { asm volatile("st.shared.v2.u32 [%0], {%1,%2};" ::"r"(a), "r"(x), "r"(y) : "memory"); }
__device__ __forceinline__ void sts4(uint32_t a, uint4 v) {
  asm volatile("st.shared.v4.u32 [%0], {%1,%2,%3,%4};" ::"r"(a), "r"(v.x), "r"(v.y), "r"(v.z), "r"(v.w) : "memory");
}
__device__ __forceinline__ float silu_f(float v) { return __fdividef(v, 1.f + __expf(-v)); }
__device__ __forceinline__ uint32_t hfma2(uint32_t a, uint32_t b, uint32_t c) {
  uint32_t r; asm("fma.rn.bf16x2 %0, %1, %2, %3;" : "=r"(r) : "r"(a), "r"(b), "r"(c)); return r;
}
__device__ __forceinline__ void split_inv(float sd, uint32_t& ih, uint32_t& il) {
  const float inv = rcp(sd);
  ih = pack_bf(inv, inv);
  const float lo = inv - bf_lo(ih);
  il = pack_bf(lo, lo);
}
__device__ __forceinline__ uint32_t ln_norm(uint32_t x, uint32_t mean2, uint32_t ih, uint32_t il) {
  const uint32_t d = hsub2(x, mean2);
  return hfma2(d, ih, hmul2(d, il));
}
__device__ __forceinline__ uint32_t modul(uint32_t n, uint32_t c1, uint32_t sh) { return hadd2(hmul2(n, c1), sh); }
__device__ __forceinline__ uint32_t ln_mod(uint32_t x, uint32_t mean2, uint32_t ih, uint32_t il, uint32_t c1, uint32_t sh) {
  return modul(ln_norm(x, mean2, ih, il), c1, sh);
}

#define R8(a, i) "+f"(a[i]), "+f"(a[i + 1]), "+f"(a[i + 2]), "+f"(a[i + 3]), "+f"(a[i + 4]), "+f"(a[i + 5]), "+f"(a[i + 6]), "+f"(a[i + 7])
#define D64 "{%0,%1,%2,%3,%4,%5,%6,%7,%8,%9,%10,%11,%12,%13,%14,%15,%16,%17,%18,%19,%20,%21,%22,%23,%24,%25,%26,%27,%28,%29,%30,%31," \
            "%32,%33,%34,%35,%36,%37,%38,%39,%40,%41,%42,%43,%44,%45,%46,%47,%48,%49,%50,%51,%52,%53,%54,%55,%56,%57,%58,%59,%60,%61,%62,%63}"
template <int TB>
__device__ __forceinline__ void mma_ss(float (&d)[64], uint64_t da, uint64_t db, int sc) {
  asm volatile("{\n.reg .pred p;\nsetp.ne.b32 p, %66, 0;\n"
               "wgmma.mma_async.sync.aligned.m64n128k16.f32.bf16.bf16 " D64 ", %64, %65, p, 1, 1, 0, %67;\n}"
               : R8(d, 0), R8(d, 8), R8(d, 16), R8(d, 24), R8(d, 32), R8(d, 40), R8(d, 48), R8(d, 56)
               : "l"(da), "l"(db), "r"(sc), "n"(TB));
}
template <int TB>
__device__ __forceinline__ void mma_rs(float (&d)[64], uint32_t a0, uint32_t a1, uint32_t a2, uint32_t a3, uint64_t db, int sc) {
  asm volatile("{\n.reg .pred p;\nsetp.ne.b32 p, %69, 0;\n"
               "wgmma.mma_async.sync.aligned.m64n128k16.f32.bf16.bf16 " D64 ", {%64,%65,%66,%67}, %68, p, 1, 1, %70;\n}"
               : R8(d, 0), R8(d, 8), R8(d, 16), R8(d, 24), R8(d, 32), R8(d, 40), R8(d, 48), R8(d, 56)
               : "r"(a0), "r"(a1), "r"(a2), "r"(a3), "l"(db), "r"(sc), "n"(TB));
}
#define D128 "{%0,%1,%2,%3,%4,%5,%6,%7,%8,%9,%10,%11,%12,%13,%14,%15,%16,%17,%18,%19,%20,%21,%22,%23,%24,%25,%26,%27,%28,%29,%30,%31," \
             "%32,%33,%34,%35,%36,%37,%38,%39,%40,%41,%42,%43,%44,%45,%46,%47,%48,%49,%50,%51,%52,%53,%54,%55,%56,%57,%58,%59,%60,%61,%62,%63," \
             "%64,%65,%66,%67,%68,%69,%70,%71,%72,%73,%74,%75,%76,%77,%78,%79,%80,%81,%82,%83,%84,%85,%86,%87,%88,%89,%90,%91,%92,%93,%94,%95," \
             "%96,%97,%98,%99,%100,%101,%102,%103,%104,%105,%106,%107,%108,%109,%110,%111,%112,%113,%114,%115,%116,%117,%118,%119,%120,%121,%122,%123,%124,%125,%126,%127}"
#define R128(d, e) R8(d, 0), R8(d, 8), R8(d, 16), R8(d, 24), R8(d, 32), R8(d, 40), R8(d, 48), R8(d, 56), \
                   R8(e, 0), R8(e, 8), R8(e, 16), R8(e, 24), R8(e, 32), R8(e, 40), R8(e, 48), R8(e, 56)
__device__ __forceinline__ void mma256_ss(float (&d)[64], float (&e)[64], uint64_t da, uint64_t db, int sc) {
  asm volatile("{\n.reg .pred p;\nsetp.ne.b32 p, %130, 0;\n"
               "wgmma.mma_async.sync.aligned.m64n256k16.f32.bf16.bf16 " D128 ", %128, %129, p, 1, 1, 0, 1;\n}"
               : R128(d, e) : "l"(da), "l"(db), "r"(sc));
}
__device__ __forceinline__ void mma256_rs(float (&d)[64], float (&e)[64], uint32_t a0, uint32_t a1, uint32_t a2, uint32_t a3, uint64_t db) {
  asm volatile("{\n.reg .pred p;\nsetp.ne.b32 p, 1, 0;\n"
               "wgmma.mma_async.sync.aligned.m64n256k16.f32.bf16.bf16 " D128 ", {%128,%129,%130,%131}, %132, p, 1, 1, 1;\n}"
               : R128(d, e) : "r"(a0), "r"(a1), "r"(a2), "r"(a3), "l"(db));
}
template <int N> __device__ __forceinline__ void keep(float (&a)[N]) {
#pragma unroll
  for (int i = 0; i < N; i++) asm volatile("" : "+f"(a[i])::"memory");
}
template <int N> __device__ __forceinline__ void keep(uint32_t (&a)[N]) {
#pragma unroll
  for (int i = 0; i < N; i++) asm volatile("" : "+r"(a[i])::"memory");
}

#define STAMP(idx) do {} while (0)
#define PROF(grp, cond, idx) do {} while (0)

constexpr float SCL2 = 1.4426950408889634f * 0.08838834764831845f;

__device__ __forceinline__ void pack_p(const float (&s)[64], uint32_t (&p)[32]) {
#pragma unroll
  for (int i = 0; i < 32; i++) p[i] = pack_bf(s[2 * i], s[2 * i + 1]);
}

__device__ __forceinline__ void issue_qk(float (&s)[64], uint32_t q0, uint32_t q1, uint32_t kslot) {
  const uint64_t db = make_desc(kslot, 16, 1024), da0 = make_desc(q0, 16, 1024), da1 = make_desc(q1, 16, 1024);
#pragma unroll
  for (int kk = 0; kk < 8; kk++) mma_ss<0>(s, (kk < 4 ? da0 : da1) + (kk & 3) * 2, db + (kk >> 2) * 1024 + (kk & 3) * 2, kk != 0);
}
__device__ __forceinline__ void issue_pv(float (&o)[64], uint32_t (&p)[32], uint32_t vslot, int acc) {
  uint64_t db = make_desc(vslot, 16384, 1024);
#pragma unroll
  for (int kk = 0; kk < 8; kk++)
    mma_rs<1>(o, p[4 * kk], p[4 * kk + 1], p[4 * kk + 2], p[4 * kk + 3], db + kk * 128, kk == 0 ? acc : 1);
}

template <int H>
__device__ __forceinline__ void store_chunk(const float (&a)[64], uint32_t addr) {
#pragma unroll
  for (int i = 8 * H; i < 8 * H + 8; i += 2)
    stmatrix4(addr ^ ((i & 7) << 4), pack_bf(a[4 * i], a[4 * i + 1]), pack_bf(a[4 * i + 2], a[4 * i + 3]),
              pack_bf(a[4 * i + 4], a[4 * i + 5]), pack_bf(a[4 * i + 6], a[4 * i + 7]));
}
template <int H>
__device__ __forceinline__ void store_chunk(const float (&a)[64], float i0, float i1, uint32_t addr) {
#pragma unroll
  for (int i = 8 * H; i < 8 * H + 8; i += 2)
    stmatrix4(addr ^ ((i & 7) << 4), pack_bf(a[4 * i] * i0, a[4 * i + 1] * i0), pack_bf(a[4 * i + 2] * i1, a[4 * i + 3] * i1),
              pack_bf(a[4 * i + 4] * i0, a[4 * i + 5] * i0), pack_bf(a[4 * i + 6] * i1, a[4 * i + 7] * i1));
}
__device__ __forceinline__ float inv_quad_sum(float l) {
  l += __shfl_xor_sync(0xffffffffu, l, 1);
  l += __shfl_xor_sync(0xffffffffu, l, 2);
  return rcp(l);
}

__device__ __forceinline__ void ln_scalars(float mean, float var, float& mb, float& sd) {
  mb = rbf(mean);
  float r; asm("sqrt.approx.ftz.f32 %0, %1;" : "=f"(r) : "f"(rbf(rbf(var) + 1e-5f)));
  sd = rbf(r);
}

__global__ void __cluster_dims__(2, 1, 1) __launch_bounds__(384, 1) fused_kernel(const __grid_constant__ Maps maps, const Ptrs P) {
  extern __shared__ __align__(1024) uint8_t smem_raw[];
  const uint32_t base = smem_u32(smem_raw);
  const int tid = threadIdx.x, lane = tid & 31;
  const int warp = __shfl_sync(0xffffffffu, tid >> 5, 0);
  const int b = blockIdx.x;
  PROF(31, tid == 0, 0);

  if (b >= NMAIN) {
    float* sc = reinterpret_cast<float*>(smem_raw);
    float* red = sc + DM;
    for (int k = tid; k < DM; k += 384) sc[k] = rbf(silu_f(__bfloat162float(P.c[k])));
    __syncthreads();
    if (tid < 256) {
      const int col = 2048 + (b - NMAIN) * 1024 + (tid & 127) * 8, r0 = (tid >> 7) * 512;
      float acc[8];
#pragma unroll
      for (int e = 0; e < 8; e++) acc[e] = 0.f;
#pragma unroll 1
      for (int r = r0; r < r0 + 512; r += HU) {
        uint4 w[HU];
#pragma unroll
        for (int u = 0; u < HU; u++) w[u] = ldg_stream4(P.w_mod + (size_t)(r + u) * NMOD + col);
#pragma unroll
        for (int u = 0; u < HU; u++) {
          float s = sc[r + u];
          acc[0] += s * bf_lo(w[u].x); acc[1] += s * bf_hi(w[u].x); acc[2] += s * bf_lo(w[u].y); acc[3] += s * bf_hi(w[u].y);
          acc[4] += s * bf_lo(w[u].z); acc[5] += s * bf_hi(w[u].z); acc[6] += s * bf_lo(w[u].w); acc[7] += s * bf_hi(w[u].w);
        }
      }
      if (tid >= 128) {
#pragma unroll
        for (int e = 0; e < 8; e++) red[(tid & 127) * 8 + e] = acc[e];
      }
      const uint32_t tag = ld_relaxed(&g_epoch) % 3 + 1;
      bar_sync(1, 256);
      if (tid < 128) {
        uint32_t o[8];
#pragma unroll
        for (int e = 0; e < 8; e++) o[e] = __float_as_uint(rbf(acc[e] + red[tid * 8 + e])) | tag;
        st_relaxed4(g_mod + col, o[0], o[1], o[2], o[3]);
        st_relaxed4(g_mod + col + 4, o[4], o[5], o[6], o[7]);
        const uint4 wr = ldg_nc4(P.w_r + tid * 8);
        const uint32_t wv[4] = {wr.x, wr.y, wr.z, wr.w};
        float dsum = 0.f;
#pragma unroll
        for (int e = 0; e < 8; e++) {
          const float m = bf_hi(o[e]);
          dsum += (b == NMAIN + 2 ? rbf(1.f + m) : m) * ((e & 1) ? bf_hi(wv[e >> 1]) : bf_lo(wv[e >> 1]));
        }
#pragma unroll
        for (int k = 16; k > 0; k >>= 1) dsum += __shfl_xor_sync(0xffffffffu, dsum, k);
        if (lane == 0) st_relaxed(g_mod + (b - NMAIN) * 4 + warp, tagf(dsum, tag));
      }
    }
    PROF(2, tid == 0, 1);
    return;
  }

  const int rank = b & 1;
  const int rb = ((b >> 4) << 1) | rank, cj = (b >> 1) & 7;
  const uint32_t bfull = base + OFF_BAR, bempty = bfull + NSLOT * 8;
  const uint32_t gfull = bempty + NSLOT * 8, gempty = gfull + 32;
  const uint32_t bar_ofull = gempty + 32;
  const uint32_t bar_ofree = bar_ofull + 32;
  const uint32_t bar_par = bar_ofree + 32;
  const uint32_t bar_mod = bar_par + 8;
  const uint32_t bar_pread = bar_mod + 8;
  const uint32_t bar_xres = bar_pread + 8;
  const uint32_t bar_ring = bar_xres + 8;
  const uint32_t bar_box = bar_ring + 24;
  const uint32_t bar_go = bar_box + 96;
  const uint32_t bar_go2 = bar_go + 16;
  const uint32_t bar_cnt = bar_go + 24;
  const uint32_t xfull = bar_go + 32, xempty = xfull + 32;
  const uint32_t bar_hw = xempty + 32, bar_hx = bar_hw + 8;
  const uint32_t bar_hpub = bar_hx + 16;
  const uint32_t bar_win = bar_hpub + 8;
  const uint32_t bar_rx = bar_win + 8;
  const uint32_t bar_sel = bar_rx + 8;
  const uint32_t bar_gate = bar_sel + 8;
  const uint32_t bar_rel = bar_gate + 8;
  const uint32_t bar_od = bar_rel + 8;
  const uint32_t bar_res = bar_go + 8;
  const uint32_t stage = base + OFF_STAGE, par = base + OFF_PAR;

  if (warp == 8 && elect_one()) {
    for (int s = 0; s < NSLOT; s++) { mbar_init(bfull + s * 8, 1); mbar_init(bempty + s * 8, 16); }
    for (int s = 0; s < 4; s++) { mbar_init(gfull + s * 8, 1); mbar_init(gempty + s * 8, 16); mbar_init(xfull + s * 8, 1); mbar_init(xempty + s * 8, 8); mbar_init(bar_ofree + s * 8, 1); mbar_init(bar_ofull + s * 8, 128); }
    mbar_init(bar_par, 64); mbar_init(bar_mod, 256); mbar_init(bar_pread, 8); mbar_init(bar_xres, 1);
    mbar_init(bar_ring, 8); mbar_init(bar_ring + 8, 8); mbar_init(bar_ring + 16, 8);
    mbar_init(bar_go, 1); mbar_init(bar_go2, 1); mbar_init(bar_cnt, 1); mbar_init(bar_hpub, 8); mbar_init(bar_res, 1); mbar_init(bar_win, 1); mbar_init(bar_rx, 1); mbar_init(bar_sel, 64); mbar_init(bar_gate, 8); mbar_init(bar_rel, 8); mbar_init(bar_od, 1);
    for (int s = 0; s < 12; s++) mbar_init(bar_box + s * 8, 1);
    asm volatile("fence.mbarrier_init.release.cluster;" ::: "memory");
    prefetch_map(&maps.x); prefetch_map(&maps.wq); prefetch_map(&maps.k); prefetch_map(&maps.v);
  }
  if (warp == 9 && elect_one()) {
    mbar_init(bar_hw, 1); mbar_init(bar_hx, 1); mbar_init(bar_hx + 8, 1);
    asm volatile("fence.mbarrier_init.release.cluster;" ::: "memory");
    mbar_expect_tx(bar_hw, 32768);
    mbar_expect_tx(bar_hx, 16384);
    mbar_expect_tx(bar_hx + 8, 16384);
    const __nv_bfloat16* xs = P.x + (size_t)(rb * 128 + cj * 16) * DM;
    bulk_load(base + 2 * GST_BYTES, xs, 16384, bar_hx);
    tma2d(stage, &maps.wm, (b >> 1) * 32, rank * 512, bar_hw);
    tma2d(stage + 16384, &maps.wm, (b >> 1) * 32, rank * 512 + 256, bar_hw);
    bulk_load(base + 3 * GST_BYTES, xs + 8 * DM, 16384, bar_hx + 8);
  }
  cluster_arrive();

  if (warp >= 8) {
    asm volatile("setmaxnreg.dec.sync.aligned.u32 40;");
    if (warp < 10) bar_arrive(1, 320);
    const uint32_t epoch = ld_relaxed(&g_epoch);
    cluster_wait();
    if (warp == 8) {
      const int kvrow = (cj >> 1) * SK + (SK - WIN);
      int wch = cj * 8 + rank * 2;
#pragma unroll 1
      for (int ps = 0; ps < 3; ps++) {
        const CUtensorMap* mw = ps == 2 ? &maps.wo : &maps.wq;
        const uint32_t xt = ps == 1 ? XT1 : XT2, wt = ps == 0 ? WT0 : (ps == 1 ? WT1 : WT2);
        const int nst = ps == 2 ? 32 : 16;
#pragma unroll 1
        for (int i = 0; i < nst; i++) {
          const uint32_t bf = gfull + (i & 3) * 8;
          const int kt = ps == 2 ? (((cj & 1) * 4 + ((i >> 1) & 3)) * 4 + (i >> 3)) * 2 + (i & 1) : (i + (ps ? 0 : b & 14)) & 15;
          const uint32_t wd = base + unit_of(wt, i & 3) + rank * UNIT, xd = base + unit_of(xt, i & 3);
          const uint8_t* xs = g_act + (uint32_t)(rb * 80 + (ps - 1) * 16 + kt) * UNIT;
          if (ps == 0 && i == HD) mbar_wait(bar_mod, 0);
          const bool xfirst = ps && i < 2;
          if (ps == 2 && i == 0) mbar_wait(bar_ofree + 24, 0);
          if (i == 0) fence_async();
          mbar_wait(gempty + (i & 3) * 8, ((i >> 2) & 1) ^ 1);
          if (elect_one()) {
            mbar_expect_tx(bf, ps ? GST_BYTES : 2 * UNIT);
            if (xfirst) bulk_load_stream(xd, xs, UNIT, bf);
          }
          if (ps && i < 4) mbar_wait(bempty + i * 8, 1);
          if (elect_one()) tma3d_mc<true>(wd, mw, 0, (i == 31 ? kt ^ (rank * 32) : kt) * 64, i == 31 ? cj * 2 : wch, bf);
          if (ps) {
            if (i == 16) { mbar_wait(bar_cnt, 0); fence_async(); }
            if (i == 2) mbar_wait(bar_ofree + (ps - 1) * 16, 0);
            if (elect_one()) {
              if (i == 31) bulk_load(xd, xs, UNIT, bf); else if (!xfirst) bulk_load_stream(xd, xs, UNIT, bf);
              mbar_arrive_pred(bar_go, i == GOST - 1);
              mbar_arrive_pred(bar_od, i == ODS);
              mbar_arrive_pred(bar_res, ((1u << RES0 | 1u << RES1) >> i) & 1);
            }
          }
        }
        if (ps == 2) break;
        wch = ps ? ((wch >> 3) ^ rank) * 2 : wch + 4;
#pragma unroll 1
        for (int u = 0; u < 16; u++) {
          const bool isk = (u == 0) || ((u & 1) && u < 15);
          const int blk = (isk ? (u + 1) >> 1 : (u == 15 ? 7 : (u >> 1) - 1)) & 3;
          const uint32_t sl = base + unit_of(ps ? AT1 : AT0, u & 3) + rank * UNIT, bf = bfull + (u & 3) * 8;
          if (u < 4) mbar_wait(gempty + ((u + 1) >> 1) * 8, 1);
          mbar_wait(bempty + (u & 3) * 8, ((u >> 2) & 1) ^ 1);
          if (elect_one()) {
            mbar_arrive_pred(bar_go2, ps && u == PG0);
            mbar_expect_tx(bf, SLOT_BYTES);
            tma3d_mc<false>(sl, isk ? &maps.k : &maps.v, 0, kvrow + blk * 128, rank, bf);
          }
        }
      }
      if (elect_one()) mbar_expect_tx(bar_rx, UNIT);
      mbar_wait(bar_rel, 0);
      if (elect_one()) {
        bulk_load_stream(base + UNIT, g_act + (uint32_t)(rb * 80 + 16 + 63 - (cj & 1) * 32) * UNIT, UNIT, bar_rx);
      }
      if (b < NFFN) {
#pragma unroll 1
        for (int u = 0; u < 12; u++) {
          const uint32_t dst = base + unit_of(u < 4 ? FT_G : (u < 8 ? FT_U : FT_D), u & 3);
          if (elect_one()) mbar_expect_tx(bar_box + u * 8, UNIT);
          if (u == FB0 || u == 2 || u == FB2) mbar_wait(bar_ring + (u == FB2 ? 16 : (u + 6) & 8), 0);
          if (u >= FPACE) mbar_wait(bar_box + (u - FPACE) * 8, 0);
          if (elect_one()) {
            if (u < 8) tma2d(dst, u < 4 ? &maps.wg : &maps.wu, b * 32, (u & 3) * 256, bar_box + u * 8);
            else tma3d(dst, &maps.wd, 0, b * 32, (u - 8) * 4, bar_box + u * 8);
          }
        }
      }
    } else if (warp == 9) {
      const uint32_t target = 8 * (epoch + 1);
#pragma unroll 1
      for (int i = 0; i < 16; i++) {
        if (i == HDX) mbar_wait(bar_mod, 0);
        if (i == NRS) {
          wait_counter(&g_cnt_h[rb * 32], target);
          PROF(1, lane == 0, 26);
          fence_async();
        }
        mbar_wait(xempty + (i & 3) * 8, ((i >> 2) & 1) ^ 1);
        if (elect_one()) {
          mbar_expect_tx(xfull + (i & 3) * 8, UNIT);
          if (i < NRS) tma2d(base + (i & 3) * GST_BYTES, &maps.x, ((2 * cj + i) & 15) * 64, rb * 128, xfull + (i & 3) * 8);
          else bulk_load_stream(base + (i & 3) * GST_BYTES, g_act + (uint32_t)(rb * 80 + ((2 * cj + i) & 15)) * UNIT, UNIT, xfull + (i & 3) * 8);
        }
      }
      prefetch_map(&maps.wo);
#pragma unroll 1
      for (int t = 0; t < 4; t++) {
        if (t & 1) mbar_wait(bar_od, t >> 1);
#pragma unroll 1
        for (int p = 0; p < 32768 / OPS; p++) {
          const uint32_t w = p / (16384 / OPS), c = (p / (8192 / OPS)) & 1, off = w * 8192 + (p % (8192 / OPS)) * OPS;
          mbar_wait(bar_ofull + (t & 1) * 16 + w * 8, t >> 1);
          if (elect_one()) {
            bulk_store(g_act + (uint32_t)(rb * 80 + 16 + (cj * 4 + t) * 2 + c) * UNIT + off, base + unit_of(QT, 2 * t + c) + off, OPS);
            asm volatile("cp.async.bulk.commit_group;" ::: "memory");
            asm volatile("cp.async.bulk.wait_group.read %0;" ::"n"(OFL) : "memory");
          }
        }
        if (elect_one()) {
          asm volatile("cp.async.bulk.wait_group.read 0;" ::: "memory");
          mbar_arrive_pred(bar_ofree + t * 8, t < 3);
          asm volatile("cp.async.bulk.wait_group 0;" ::: "memory");
          fence_async();
          red_release(&g_cnt_o[((rb * 4 + t) * 2 + (cj >> 2)) * 32], 2);
        }
        if (t & 1) {
          wait_counter(&g_cnt_o[(rb * 8 + 2 * t - 2 + (cj & 1)) * 32], target);
          wait_counter(&g_cnt_o[(rb * 8 + 2 * t + (cj & 1)) * 32], target);
          if (elect_one()) mbar_arrive_pred(bar_ofree + 24, t == 1);
        }
      }
      wait_counter(&g_cnt_o[(rb * 8 + 7 - (cj & 1)) * 32], target);
      fence_async();
      if (elect_one()) {
        mbar_arrive(bar_cnt);
        PROF(2, true, 27);
        mbar_expect_tx(bar_xres, 32768);
      }
#pragma unroll 1
      for (int u = 0; u < 2; u++) {
        mbar_wait(bar_res, u);
        if (elect_one()) tma2d(base + OFF_RES + u * UNIT, &maps.x, cj * 128 + u * 64, rb * 128, bar_xres);
      }
      const uint32_t tag = epoch % 3 + 1;
      const uint32_t* inbox = g_cand + (lane & 15);
      mbar_wait(bar_ring + 16, 0);
      uint32_t c0 = ld_relaxed(inbox), n = 0;
#define CAND_STEP(cv)                                                                                        \
      {                                                                                                      \
        const bool valid = (cv & 3u) == tag, all = __all_sync(0xffffffffu, valid);                           \
        const uint32_t best = __reduce_max_sync(0xffffffffu, valid ? cv : 0u);                               \
        const uint32_t blk = __ffs(__ballot_sync(0xffffffffu, cv == best)) - 1;                              \
        if (best) sts2(par + PAR_CONST + 56, best, (blk << 7 | (~best >> 2 & 127)) | (all ? 0x1800 : 0x800)); \
        if (all) break;                                                                                      \
        cv = ld_relaxed(inbox);                                                                              \
      }
      while (true) { CAND_STEP(c0) watchdog(n); }
    } else {
      const int t2 = tid - 320;
      if (t2 == 0) {
        mbar_wait(bar_hpub, 0);
        PROF(1, true, 24);
        red_release(&g_cnt_h[rb * 32], 1);
        PROF(1, true, 25);
        prefetch_map(&maps.wg); prefetch_map(&maps.wu); prefetch_map(&maps.wd); prefetch_map(&maps.out);
      }
      __syncwarp();
      if (b < NFFN) {
        mbar_wait(bar_go2, 0);
        const __nv_bfloat16* pg = ((b & 1) ? P.w_up : P.w_gate) + (b >> 1) * 64 + (size_t)t2 * FF;
        const __nv_bfloat16* pd = P.w_down + (size_t)b * 32768 + t2 * 64;
        PROF(2, t2 == 0, 13);
#pragma unroll 1
        for (int i = 0; i < WN; i += WB) {
          uint32_t v[WB];
#pragma unroll
          for (int u = 0; u < WB; u++) {
            const int k = i + u;
            asm volatile("ld.global.cg.L2::128B.u32 %0, [%1];" : "=r"(v[u]) : "l"(k < 16 ? pg + (size_t)k * 64 * FF : pd + (k - 16) * 4096));
          }
#pragma unroll
          for (int u = 1; u < WB; u++) v[0] ^= v[u];
          sts1(par + PAR_SINK + t2 * 4, v[0]);
        }
        PROF(2, t2 == 0, 14);
      }
      const uint32_t tag = epoch % 3 + 1;
      mbar_wait(bar_go, 0);
      if (warp == 10) {
        const uint32_t* src = g_mod + 2 * DM + cj * 128 + lane * 4;
        const uint2 wr = *reinterpret_cast<const uint2*>(P.w_r + cj * 128 + lane * 4);
        uint4 vga, vsb, vcb, vgb;
        uint32_t n = 0;
        do {
          vga = ld_relaxed4(src); vsb = ld_relaxed4(src + DM); vcb = ld_relaxed4(src + 2 * DM); vgb = ld_relaxed4(src + 3 * DM);
          watchdog(n);
        } while (!__all_sync(0xffffffffu, tag_ok(vga, tag) && tag_ok(vsb, tag) && tag_ok(vcb, tag) && tag_ok(vgb, tag)));
        const float c0 = rbf(1.f + bf_hi(vcb.x)), c1 = rbf(1.f + bf_hi(vcb.y)), c2 = rbf(1.f + bf_hi(vcb.z)), c3 = rbf(1.f + bf_hi(vcb.w));
        const float a0 = c0 * bf_lo(wr.x), a1 = c1 * bf_hi(wr.x), a2 = c2 * bf_lo(wr.y), a3 = c3 * bf_hi(wr.y);
        const uint32_t h0 = pack_bf(a0, a1), h1 = pack_bf(a2, a3);
        const uint32_t t1 = par + PAR_T1 + (lane >> 2) * 64 + (lane & 1) * 32 + (lane & 2) * 2;
        sts1(t1, h0); sts1(t1 + 8, pack_bf(a0 - bf_lo(h0), a1 - bf_hi(h0)));
        sts1(t1 + 16, h1); sts1(t1 + 24, pack_bf(a2 - bf_lo(h1), a3 - bf_hi(h1)));
        sts4(par + PAR_T2 + lane * 32, make_uint4(pack_bf(c0, c1), __byte_perm(vsb.x, vsb.y, 0x7632), __byte_perm(vgb.x, vgb.y, 0x7632), __byte_perm(vga.x, vga.y, 0x7632)));
        sts4(par + PAR_T2 + lane * 32 + 16, make_uint4(pack_bf(c2, c3), __byte_perm(vsb.z, vsb.w, 0x7632), __byte_perm(vgb.z, vgb.w, 0x7632), __byte_perm(vga.z, vga.w, 0x7632)));
      } else {
        const uint4 g = poll4((lane & 2) ? g_mod + 8 - (lane & 1) * 4 : g_mod + 5 * DM + b * 8 + (lane & 1) * 4, tag);
        sts1(par + PAR_CONST + 60, 0);
        if (lane < 2) sts4(par + PAR_CONST + 16 + lane * 16, g);
        else if (lane < 4) sts2(par + PAR_CONST + (lane - 2) * 8, __float_as_uint(untag_sum(g.x, g.y) + untag_sum(g.z, g.w)), epoch);
      }
      __syncwarp();
#pragma unroll 4
      for (int q = XR; q < XE; q++) st_b128(g_xch + ((size_t)b * 8 * 256 + q * 64 + t2) * 4, (epoch & 1) << 16, 0, 0, 0);
      for (int q = 0; q < 2; q++) st_relaxed4(g_stats + ((size_t)cj * SEQ + rb * 128 + q * 64 + t2) * 4, 0, 0, 0, 0);
      if (b < NFFN)
        for (int q = 0; q < 4; q++) st_relaxed4(g_ypart + ((size_t)(q * 32 + (t2 >> 1)) * NFFN + b) * 8 + (t2 & 1) * 4, 0, 0, 0, 0);
      st_relaxed4(g_row + rb * 2 * DM + (t2 >> 5) * DM + cj * 128 + (t2 & 31) * 4, 0, 0, 0, 0);
      __threadfence();
      mbar_arrive(bar_par);
      mbar_wait(bar_gate, 0);
      uint32_t have = 0, n = 0;
      while (true) {
        const uint32_t st = lds1(par + PAR_CONST + 60) >> 7;
        if ((st & 31) != have) {
          const uint32_t* hsrc = g_row + (st & 15) * 2 * DM + t2 * 4;
          uint4 hv[4];
          bool ok = true;
#pragma unroll
          for (int i = 0; i < 4; i++) hv[i] = ld_pairs(hsrc + i * 256);
#pragma unroll
          for (int i = 0; i < 4; i++) {
            sts2(base + ((FT_G >> i * 4) & 15) * UNIT + (warp & 1) * 8192 + 256 + lane * 8, hv[i].x, hv[i].z);
            ok = ok && hv[i].y == tag && hv[i].w == tag;
          }
          have = __all_sync(0xffffffffu, ok) ? st & 31 : 0;
        }
        if ((st ^ have) == 32) break;
        watchdog(n);
      }
      mbar_arrive(bar_sel);
    }
    __syncwarp();
    cluster_arrive();
    {
      const uint32_t tag = epoch % 3 + 1, t3 = tid - 256;
      mbar_wait(bar_win, 0);
      uint2 win = lds2(par + PAR_CONST + 56);
      win.y &= 0x7ff;
      const uint32_t* fsrc = g_row + (win.y >> 7) * 2 * DM + (b >> 1) * 16 + (t3 & 3) * 4 + (b & 1) * 2;
      const uint32_t* ysrc = g_ypart + (size_t)b * NFFN * 8 + min(t3, NFFN - 1) * 4;
      uint2 fh = ld_pair(fsrc), fx = ld_pair(fsrc + DM);
      if (PSL) __nanosleep(PSL);
      uint4 ya = ld_relaxed4(ysrc), yb = ld_relaxed4(ysrc + NFFN * 4);
      const float rwin = __uint_as_float(((int)win.x < 0 ? win.x & 0x7fffffffu : ~win.x) & ~0x1ffu);
      const float rs = rbf(rcp(1.f + __expf(-rbf(rwin))));
      uint32_t n = 0;
      while (__any_sync(0xffffffffu, fh.y != tag || fx.y != tag)) { fh = ld_pair(fsrc); fx = ld_pair(fsrc + DM); watchdog(n); }
      while (!__all_sync(0xffffffffu, tag_ok(ya, tag) && tag_ok(yb, tag))) {
        if (!tag_ok(ya, tag)) ya = ld_relaxed4(ysrc);
        if (!tag_ok(yb, tag)) yb = ld_relaxed4(ysrc + NFFN * 4);
        watchdog(n);
      }
      __syncwarp();
      PROF(8, t3 == 0, 5);
      float y0 = untag_sum(ya.x, yb.x), y1 = untag_sum(ya.y, yb.y), y2 = untag_sum(ya.z, yb.z), y3 = untag_sum(ya.w, yb.w);
      const bool u1 = lane & 2, u2 = lane & 4;
      y0 = (u1 ? y2 : y0) + __shfl_xor_sync(0xffffffffu, u1 ? y0 : y2, 2);
      y1 = (u1 ? y3 : y1) + __shfl_xor_sync(0xffffffffu, u1 ? y1 : y3, 2);
      y0 = (u2 ? y1 : y0) + __shfl_xor_sync(0xffffffffu, u2 ? y0 : y1, 4);
      y0 += __shfl_xor_sync(0xffffffffu, y0, 8);
      if (!(lane & 8)) sts1(par + PAR_RED + 64 + (t3 >> 4) * 32 + ((lane & 1) * 4 + (lane & 2) + ((lane >> 2) & 1)) * 4, __float_as_uint(y0));
      bar_sync(4, 128);
      if (t3 < 4) {
        y0 = 0.f; y1 = 0.f;
#pragma unroll
        for (int w4 = 0; w4 < 7; w4++) {
          const uint2 v = lds2(par + PAR_RED + 64 + w4 * 32 + t3 * 8);
          y0 += __uint_as_float(v.x); y1 += __uint_as_float(v.y);
        }
        const uint2 gv = lds2(par + PAR_CONST + 16 + t3 * 8);
        const uint32_t upd = hmul2(pack_bf(y0, y1), pack_bf(rs, rs));
        *reinterpret_cast<uint32_t*>(P.out + (size_t)win.y * DM + b * 8 + t3 * 2) =
            hadd2(fx.x, hmul2(__byte_perm(gv.x, gv.y, 0x7632), hadd2(fh.x, upd)));
        if (b == 0 && t3 == 0) st_relaxed(&g_epoch, epoch + 1);
      }
      PROF(31, t3 == 0, 36);
    }
    cluster_wait();
  } else {
    const int wg = warp >> 2;

    uint32_t tag;
    {
      uint32_t* const pmod = g_modp + rank * 2 * DM + (b >> 1) * 32 + lane;
      uint32_t* const pln = g_ln1 + (rb * 128 + cj * 16 + warp) * 4;
      const uint32_t cv = ldg_nc1(P.c + rank * 512 + tid * 2);
      const uint32_t epoch = ld_relaxed(&g_epoch);
      if (warp == 0) st_relaxed(pmod, 0);
      if (lane == 0) { st_b128(pln, 0, 0, 0, 0); st_b128(pln + 32, 0, 0, 0, 0); }
      asm volatile("setmaxnreg.inc.sync.aligned.u32 232;");
      sts1(par + tid * 4, pack_bf(silu_f(bf_lo(cv)), silu_f(bf_hi(cv))));
      bar_sync(1, 320);
      tag = epoch % 3 + 1;
#pragma unroll
      for (int part = 0; part < 3; part++) {
        if (part != 1) {
          const uint32_t xa = base + (2 + part / 2) * GST_BYTES + warp * 2048 + lane * 16;
          mbar_wait(bar_hx + part * 4, 0);
          float s0 = 0.f, s1 = 0.f, q0 = 0.f, q1 = 0.f;
#pragma unroll
          for (int q = 0; q < 4; q++) {
            const uint4 xv = lds4(xa + q * 512);
            const uint32_t u[4] = {xv.x, xv.y, xv.z, xv.w};
#pragma unroll
            for (int e = 0; e < 4; e++) { const float lo = bf_lo(u[e]), hi = bf_hi(u[e]); s0 += lo; s1 += hi; q0 += lo * lo; q1 += hi * hi; }
          }
          s0 += s1; q0 += q1;
#pragma unroll
          for (int o = 16; o > 0; o >>= 1) { s0 += __shfl_xor_sync(0xffffffffu, s0, o); q0 += __shfl_xor_sync(0xffffffffu, q0, o); }
          const float mean = s0 * (1.f / DM);
          float mb, sd;
          ln_scalars(mean, fmaxf(q0 * (1.f / DM) - mean * mean, 0.f), mb, sd);
          uint32_t ih, il;
          split_inv(sd, ih, il);
          if (lane == 0) st_b128(pln + part * 16, pack_bf(mb, mb), ih, il, tag);
          PROF(1, tid == 0 && part == 2, 4);
        } else {
          float acc[8];
#pragma unroll
          for (int e = 0; e < 8; e++) acc[e] = 0.f;
          const uint32_t wa = stage + (tid >> 2) * 64 + (((tid ^ (tid >> 3)) & 3) << 4), sa = par + (tid >> 3) * 4, sh = (tid & 4) ? 0x3244 : 0x1044;
          mbar_wait(bar_hw, 0);
#pragma unroll
          for (int p = 0; p < 8; p++) {
            const uint4 w = lds4(wa + p * 4096);
            const float s = __uint_as_float(__byte_perm(lds1(sa + p * 128), 0, sh));
            acc[0] += s * bf_lo(w.x); acc[1] += s * bf_hi(w.x); acc[2] += s * bf_lo(w.y); acc[3] += s * bf_hi(w.y);
            acc[4] += s * bf_lo(w.z); acc[5] += s * bf_hi(w.z); acc[6] += s * bf_lo(w.w); acc[7] += s * bf_hi(w.w);
          }
#pragma unroll
          for (int e = 0; e < 4; e++) {
            const bool up = lane & 16;
            acc[e] = (up ? acc[e + 4] : acc[e]) + __shfl_xor_sync(0xffffffffu, up ? acc[e] : acc[e + 4], 16);
          }
#pragma unroll
          for (int e = 0; e < 2; e++) {
            const bool up = lane & 8;
            acc[e] = (up ? acc[e + 2] : acc[e]) + __shfl_xor_sync(0xffffffffu, up ? acc[e] : acc[e + 2], 8);
          }
          {
            const bool up = lane & 4;
            acc[0] = (up ? acc[1] : acc[0]) + __shfl_xor_sync(0xffffffffu, up ? acc[0] : acc[1], 4);
          }
          sts1(par + 1024 + warp * 128 + ((lane & 3) * 8 + (lane >> 2)) * 4, __float_as_uint(acc[0]));
          bar_sync(1, 256);
          if (warp == 0) {
            float s = 0.f;
#pragma unroll
            for (int w8 = 0; w8 < 8; w8++) s += __uint_as_float(lds1(par + 1024 + w8 * 128 + lane * 4));
            st_relaxed(pmod, (__float_as_uint(s) & ~3u) | tag);
          }
          PROF(1, tid == 0, 3);
        }
      }
      cluster_wait();
      if (wg == 1) bar_arrive(2, 256);
    }

    float f0 = 0.f, f1 = 0.f;
    const uint32_t rempty = lane < 2 ? mapa(bempty, lane & 1) : 0;
    constexpr uint32_t GE = NSLOT * 8 + 32;
    float o[64], s[64];
#pragma unroll 1
    for (int ps = 0; ps < 3; ps++) {
      {
        const uint32_t xt = ps == 1 ? XT1 : XT2, wt = ps == 1 ? WT1 : WT2;
        const int nst = ps == 2 ? 28 : 14;
        if (ps == 0) {
          float ga[64], gb[64];
#pragma unroll
          for (int i = 0; i < 64; i++) { ga[i] = 0.f; gb[i] = 0.f; }
          uint32_t a[2][16];
          const uint32_t l = fresh_lane();
          auto fetch = [&](int i, uint32_t (&f)[16], uint32_t z) {
            const uint32_t ad = base + (i & 3) * GST_BYTES + wg * 8192 + frag_offset(warp) + z;
            mbar_wait(xfull + (i & 3) * 8, i >> 2);
#pragma unroll
            for (int kk = 0; kk < 4; kk++) ldmatrix4(ad ^ (kk * 32), f[4 * kk], f[4 * kk + 1], f[4 * kk + 2], f[4 * kk + 3]);
          };
          uint4 r0, r1;
          {
            const uint32_t t7 = (warp & 3) * 32 + l;
            const uint32_t* pm = g_modp + wg * DM + ((cj * 128 + t7 * 4) & (DM - 1));
            const uint32_t* pr = g_ln1 + (rb * 128 + warp * 16 + (l >> 2)) * 4;
            uint4 m0 = ld_relaxed4(pm), m1 = ld_relaxed4(pm + 2 * DM);
            r0 = ld_b128(pr); r1 = ld_b128(pr + 32);
            fetch(0, a[0], 0); fetch(1, a[1], 0);
            uint32_t n = 0;
            bool written = false;
#pragma unroll 1
            while (true) {
              uint32_t miss;
              asm volatile("{ .reg .pred p0, p1, p2, p3; .reg .b32 t, u;\n"
                           "lop3.b32 t, %1, %2, %19, 0x7e; lop3.b32 u, %3, %4, %19, 0x7e; or.b32 t, t, u; and.b32 t, t, 3; setp.ne.u32 p0, t, 0;\n"
                           "lop3.b32 t, %5, %6, %19, 0x7e; lop3.b32 u, %7, %8, %19, 0x7e; or.b32 t, t, u; and.b32 t, t, 3; setp.ne.u32 p1, t, 0;\n"
                           "setp.ne.u32 p2, %12, %19; setp.ne.u32 p3, %16, %19;\n"
                           "@p0 ld.relaxed.gpu.global.v4.u32 {%1, %2, %3, %4}, [%17];\n"
                           "@p1 ld.relaxed.gpu.global.v4.u32 {%5, %6, %7, %8}, [%17 + 8192];\n"
                           "@p2 ld.relaxed.gpu.global.v4.u32 {%9, %10, %11, %12}, [%18];\n"
                           "@p3 ld.relaxed.gpu.global.v4.u32 {%13, %14, %15, %16}, [%18 + 128];\n"
                           "or.pred p0, p0, p1; or.pred p2, p2, p3; vote.sync.any.pred p0, p0, 0xffffffff; vote.sync.any.pred p2, p2, 0xffffffff;\n"
                           "selp.u32 t, 1, 0, p0; selp.u32 u, 2, 0, p2; or.b32 %0, t, u; }"
                           : "=r"(miss), "+r"(m0.x), "+r"(m0.y), "+r"(m0.z), "+r"(m0.w), "+r"(m1.x), "+r"(m1.y), "+r"(m1.z), "+r"(m1.w),
                             "+r"(r0.x), "+r"(r0.y), "+r"(r0.z), "+r"(r0.w), "+r"(r1.x), "+r"(r1.y), "+r"(r1.z), "+r"(r1.w)
                           : "l"(pm), "l"(pr), "r"(tag) : "memory");
              if (!(miss & 1) && !written) {
                written = true;
                float c0 = untag_sum(m0.x, m1.x), c1 = untag_sum(m0.y, m1.y), c2 = untag_sum(m0.z, m1.z), c3 = untag_sum(m0.w, m1.w);
                if (wg) { c0 = 1.f + rbf(c0); c1 = 1.f + rbf(c1); c2 = 1.f + rbf(c2); c3 = 1.f + rbf(c3); }
                const uint32_t d = stage + (t7 >> 2) * 64 + (t7 & 1) * 32 + (t7 & 2) * 2 + (wg ? 0 : 8);
                sts1(d, pack_bf(c0, c1));
                sts1(d + 16, pack_bf(c2, c3));
                mbar_arrive(bar_mod);
              }
              if (!miss) break;
              watchdog(n);
            }
          }
          const uint32_t zero = r0.w ^ tag;
          auto normalize = [&](uint32_t (&f)[16]) {
#pragma unroll
            for (int k = 0; k < 16; k += 2) { f[k] = ln_norm(f[k], r0.x, r0.y, r0.z); f[k + 1] = ln_norm(f[k + 1], r1.x, r1.y, r1.z); }
          };
          auto modulate = [&](int i, uint32_t (&f)[16]) {
#pragma unroll
            for (int kk = 0; kk < 4; kk++) {
              const uint4 m = lds4(stage + (l & 3) * 16 + i * 256 + kk * 64);
              f[4 * kk] = modul(f[4 * kk], m.x, m.z); f[4 * kk + 1] = modul(f[4 * kk + 1], m.x, m.z);
              f[4 * kk + 2] = modul(f[4 * kk + 2], m.y, m.w); f[4 * kk + 3] = modul(f[4 * kk + 3], m.y, m.w);
            }
            keep(f);
            mbar_arrive_pred(xempty + (i & 3) * 8, l == 0);
          };
          auto publish = [&](int u, uint32_t (&f)[16]) {
            const uint32_t sc = stage + 8192 + wg * 8192;
#pragma unroll
            for (int kk = 0; kk < 4; kk++) stmatrix4((sc + frag_offset(warp)) ^ (kk * 32), f[4 * kk], f[4 * kk + 1], f[4 * kk + 2], f[4 * kk + 3]);
            __syncwarp();
            const uint32_t src = sc + (warp & 3) * 2048 + l * 16;
            uint8_t* dst = g_act + (uint32_t)(rb * 80 + cj * 2 + u) * UNIT + warp * 2048 + l * 16;
#pragma unroll
            for (int p4 = 0; p4 < 4; p4++) stg4(dst + p4 * 512, lds4(src + p4 * 512));
            __syncwarp();
            if (u == 1) mbar_arrive_pred(bar_hpub, l == 0);
          };
          auto multiply = [&](int i, uint32_t (&f)[16]) {
            mbar_wait(gfull + (i & 3) * 8, i >> 2);
            const uint64_t db = make_desc(base + (i & 3) * GST_BYTES + UNIT, 8192, 1024);
            wg_fence();
#pragma unroll
            for (int kk = 0; kk < 4; kk++) mma256_rs(ga, gb, f[4 * kk], f[4 * kk + 1], f[4 * kk + 2], f[4 * kk + 3], db + kk * 128);
            wg_commit();
          };
          auto next = [&](int i, uint32_t (&f)[16]) {
            wg_wait<1>();
            mbar_arrive_cl(rempty, GE + ((i + 2) & 3) * 8);
            uint32_t z = zero;
#pragma unroll
            for (int k = 0; k < 16; k += 2) asm volatile("lop3.b32 %0, %1, %2, %0, 0xA8;" : "+r"(z) : "r"(f[k]), "r"(f[k + 1]));
            fetch(i, f, z); normalize(f); modulate(i, f); multiply(i, f);
          };
          normalize(a[0]); normalize(a[1]);
          keep(a[0]); keep(a[1]);
          mbar_wait(bar_mod, 0);
          PROF(1, tid == 0, 2);
          if (PORD == 0) { modulate(0, a[0]); multiply(0, a[0]); modulate(1, a[1]); multiply(1, a[1]); publish(0, a[0]); publish(1, a[1]); }
          if (PORD == 1) { modulate(0, a[0]); multiply(0, a[0]); publish(0, a[0]); modulate(1, a[1]); multiply(1, a[1]); publish(1, a[1]); }
          if (PORD == 2) { modulate(0, a[0]); multiply(0, a[0]); publish(0, a[0]); modulate(1, a[1]); publish(1, a[1]); multiply(1, a[1]); }
#pragma unroll 1
          for (int i = 2; i < NRS; i += 2) { next(i, a[0]); next(i + 1, a[1]); }
          wg_wait<1>();
          mbar_arrive_cl(rempty, GE + ((NRS + 2) & 3) * 8);
          mbar_arrive_pred(bar_pread, l == 0);
#pragma unroll 1
          for (int i = NRS; i < 14; i++) {
            mbar_wait(xfull + (i & 3) * 8, (i >> 2) & 1);
            mbar_wait(gfull + (i & 3) * 8, (i >> 2) & 1);
            const uint32_t xa = base + (i & 3) * GST_BYTES;
            const uint64_t da = make_desc(xa + wg * 8192, 16, 1024), db = make_desc(xa + UNIT, 8192, 1024);
            if (i == 13) bar_sync(2 + wg, 256);
            wg_fence();
#pragma unroll
            for (int kk = 0; kk < 4; kk++) mma256_ss(ga, gb, da + kk * 2, db + kk * 128, 1);
            wg_commit();
            if (i == 13) bar_arrive(3 - wg, 256);
            wg_wait<1>();
            uint32_t z = zero;
#pragma unroll
            for (int k = 0; k < 16; k += 2) asm volatile("lop3.b32 %0, %1, %2, %0, 0xA8;" : "+r"(z) : "r"(a[1][k]), "r"(a[1][k + 1]));
            mbar_arrive_cl(rempty, GE + ((i + 3) & 3) * 8 + z);
            mbar_arrive_pred(xempty + ((i + 3) & 3) * 8, l == 0 && i != NRS);
          }
          mbar_wait(xfull + 16, 1);
          wg_wait<0>();
          keep(ga); keep(gb);
#pragma unroll
          for (int i = 0; i < 64; i++) {
            asm volatile("mov.b32 %0, %1;" : "=f"(s[i]) : "f"(ga[i]));
            asm volatile("mov.b32 %0, %1;" : "=f"(o[i]) : "f"(gb[i]));
          }
        } else {
          float ga[64], gb[64];
#pragma unroll
          for (int i = 0; i < 64; i++) {
            asm volatile("mov.b32 %0, %1;" : "=f"(ga[i]) : "f"(s[i]));
            asm volatile("mov.b32 %0, %1;" : "=f"(gb[i]) : "f"(o[i]));
          }
#pragma unroll 1
          for (int i = 0; i < nst; i++) {
            mbar_wait(gfull + (i & 3) * 8, (i >> 2) & 1);
            const uint64_t da = make_desc(base + unit_of(xt, i & 3) + wg * 8192, 16, 1024), db = make_desc(base + unit_of(wt, i & 3), 8192, 1024);
            if (i == nst - 1) bar_sync(2 + wg, 256);
            wg_fence();
#pragma unroll
            for (int kk = 0; kk < 4; kk++) mma256_ss(ga, gb, da + kk * 2, db + kk * 128, kk ? 1 : i);
            wg_commit();
            if (i == nst - 1) bar_arrive(3 - wg, 256);
            wg_wait<1>();
            mbar_arrive_cl(rempty, GE + ((i + 3) & 3) * 8, i != 0);
            PROF(4, tid == 0 && (i & 3) == 0, 40 + (ps - 1) * 4 + i / 4);
          }
          wg_wait<0>();
          keep(ga); keep(gb);
#pragma unroll
          for (int i = 0; i < 64; i++) {
            asm volatile("mov.b32 %0, %1;" : "=f"(s[i]) : "f"(ga[i]));
            asm volatile("mov.b32 %0, %1;" : "=f"(o[i]) : "f"(gb[i]));
          }
        }
        mbar_arrive_cl(rempty, GE + (ps == 2 ? 24 : 8));
        if (ps == 2) break;
      }
      const uint32_t qw = base + wg * 8192, qt = QT >> (16 * ps), at = ps ? AT1 : AT0;
      {
        const uint32_t wt = ps ? WT1 : WT0;
        const uint64_t da0 = make_desc(qw + unit_of(qt, 2), 16, 1024), da1 = make_desc(qw + unit_of(qt, 3), 16, 1024);
        const uint64_t db0 = make_desc(base + unit_of(wt, 2), 8192, 1024), db1 = make_desc(base + unit_of(wt, 3), 8192, 1024);
        mbar_wait(gfull + 16, 1);
        bar_sync(2 + wg, 256);
        wg_fence();
#pragma unroll
        for (int kk = 0; kk < 4; kk++) mma_ss<1>(s, da0 + kk * 2, db0 + kk * 128, 1);
        wg_commit();
        mbar_wait(xfull + 24, 1);
        mbar_wait(gfull + 24, 1);
        wg_fence();
#pragma unroll
        for (int kk = 0; kk < 4; kk++) mma_ss<1>(s, da1 + kk * 2, db1 + kk * 128, 1);
        wg_commit();
        bar_arrive(3 - wg, 256);
        mbar_wait(ps == 0 ? bar_pread : bar_ofree + 8, 0);
        mbar_wait(bfull, 0);
        wg_wait<0>();
        keep(s);
        PROF(2, tid == 0, 8 + ps * 8);
        store_chunk<0>(s, qw + unit_of(qt, 0) + frag_offset(warp));
        store_chunk<1>(s, qw + unit_of(qt, 1) + frag_offset(warp));
        fence_async_smem();
        bar_sync(2 + wg, 256);
        wg_fence();
        issue_qk(s, qw + unit_of(qt, 0), qw + unit_of(qt, 1), base + unit_of(at, 0));
        wg_commit();
#pragma unroll
        for (int kk = 0; kk < 8; kk++) mma_ss<1>(o, (kk < 4 ? da0 : da1) + (kk & 3) * 2, (kk < 4 ? db0 : db1) + UNIT / 16 + (kk & 3) * 128, 1);
        wg_commit();
        bar_arrive(3 - wg, 256);
        wg_wait<1>();
        keep(s);
        mbar_arrive_cl(rempty, 0);
      }
      PROF(4, tid == 0 && ps == 1, 61);
      float l0 = 0.25f, l1 = 0.25f;
      auto step = [&](auto odd_c, const int j, uint32_t (&pw)[32], uint32_t (&pr)[32]) {
        constexpr bool ODD = decltype(odd_c)::value;
        const bool first = !ODD && (j & 2) == 0, last = ODD && j == 7;
        const uint32_t ph = (j >> 1) & 1;
        float i0, i1, a0, a1;
        if (first) { i0 = inv_quad_sum(l0); i1 = inv_quad_sum(l1); l0 = 0.f; l1 = 0.f; }
        bool redo = !ODD && (j | ps) == 0, again = false;
        while (true) {
          if (redo) {
            float m0 = fmaxf(s[0], s[1]), m1 = fmaxf(s[2], s[3]);
#pragma unroll
            for (int i = 1; i < 16; i++) { m0 = fmaxf(m0, fmaxf(s[4 * i], s[4 * i + 1])); m1 = fmaxf(m1, fmaxf(s[4 * i + 2], s[4 * i + 3])); }
            m0 = fmaxf(m0, __shfl_xor_sync(0xffffffffu, m0, 1)); m1 = fmaxf(m1, __shfl_xor_sync(0xffffffffu, m1, 1));
            m0 = fmaxf(m0, __shfl_xor_sync(0xffffffffu, m0, 2)); m1 = fmaxf(m1, __shfl_xor_sync(0xffffffffu, m1, 2));
            m0 *= SCL2; m1 *= SCL2;
            if (!first) {
              m0 = fmaxf(m0, f0); m1 = fmaxf(m1, f1);
              const float c0 = ex2(f0 - m0), c1 = ex2(f1 - m1);
              l0 *= c0; l1 *= c1;
              wg_wait<0>();
              keep(o);
#pragma unroll
              for (int i = 0; i < 16; i++) { o[4 * i] *= c0; o[4 * i + 1] *= c0; o[4 * i + 2] *= c1; o[4 * i + 3] *= c1; }
            }
            f0 = m0; f1 = m1;
          }
          float b0 = 0.f, b1 = 0.f;
          a0 = 0.f; a1 = 0.f;
#pragma unroll
          for (int i = 0; i < 16; i++) {
            const float e0 = ex2(fmaf(s[4 * i], SCL2, -f0)), e1 = ex2(fmaf(s[4 * i + 1], SCL2, -f0));
            const float e2 = ex2(fmaf(s[4 * i + 2], SCL2, -f1)), e3 = ex2(fmaf(s[4 * i + 3], SCL2, -f1));
            a0 += e0; b0 += e1; a1 += e2; b1 += e3;
            pw[2 * i] = pack_bf(e0, e1); pw[2 * i + 1] = pack_bf(e2, e3);
            if (i == VREL) {
#pragma unroll
              for (int k = 0; k < 2 * VREL + 2; k++) asm volatile("" : "+r"(pw[k])::"memory");
              mbar_wait(bar_mod, 0);
              wg_wait<0>();
              mbar_arrive_cl(rempty, ODD ? 16 : (j ? 0 : GE + 16), !again);
              if (!ODD) mbar_arrive_cl(rempty, GE + 24, !again && j == 0);
#pragma unroll
              for (int k = 4 * VREL + 4; k < 64; k++) asm volatile("" : "+f"(s[k])::"memory");
            }
          }
          a0 += b0; a1 += b1;
          if (redo) break;
          redo = __any_sync(0xffffffffu, !(a0 + a1 < 0x1p70f));
          if (first) {
            uint32_t m0 = __ballot_sync(0xffffffffu, a0 > 0x1p-50f), m1 = __ballot_sync(0xffffffffu, a1 > 0x1p-50f);
            m0 |= m0 >> 1; m1 |= m1 >> 1; m0 |= m0 >> 2; m1 |= m1 >> 2;
            redo = redo || (m0 & m1 & 0x11111111u) != 0x11111111u;
          }
          if (!redo) break;
          again = true;
        }
        l0 += a0; l1 += a1;
        keep(pw);
        keep(o);
        const uint32_t qo = qt >> (j ? 0 : 8);
        if (first) store_chunk<0>(o, i0, i1, qw + unit_of(qo, 0) + frag_offset(warp));
        keep(o);
        mbar_wait(bfull + (ODD ? 24 : 8), ph);
        bar_sync(2 + wg, 256);
        if (!last) {
          const uint32_t qn = qt >> (j >= 3 ? 8 : 0);
          wg_fence();
          issue_qk(s, qw + unit_of(qn, 0), qw + unit_of(qn, 1), base + unit_of(at, ODD ? 3 : 1));
          wg_commit();
          mbar_wait(bfull + (ODD ? 0 : 16), ODD ? ph ^ 1 : ph);
        }
        if (first) { store_chunk<1>(o, i0, i1, qw + unit_of(qo, 1) + frag_offset(warp)); keep(o); }
        wg_fence();
        issue_pv(o, pw, base + unit_of(at, ODD ? (last ? 3 : 0) : 2), !first);
        wg_commit();
        bar_arrive(3 - wg, 256);
        wg_wait<1>();
        keep(s);
        mbar_arrive_cl(rempty, ODD ? 24 : 8, !last);
        if (first) { fence_async_smem(); mbar_arrive_pred(bar_ofull + wg * 8, j); }
        PROF(4, tid == 0 && ps == 1, 51 + j);
      };
      uint32_t pa[32], pb[32];
#pragma unroll 1
      for (int j = 0; j < 8; j += 2) {
        step(std::false_type{}, j, pa, pb);
        step(std::true_type{}, j + 1, pb, pa);
      }
      {
        const float i0 = inv_quad_sum(l0), i1 = inv_quad_sum(l1);
        wg_wait<0>();
        keep(o);
        mbar_arrive_cl(rempty, 24);
        store_chunk<0>(o, i0, i1, qw + unit_of(qt, 2) + frag_offset(warp));
        store_chunk<1>(o, i0, i1, qw + unit_of(qt, 3) + frag_offset(warp));
        fence_async_smem();
        mbar_arrive(bar_ofull + 16 + wg * 8);
      }
      PROF(2, tid == 0, 10 + ps * 8);
    }

    const int ln = fresh_lane(), g = ln >> 2, tq = ln & 3, ct = warp * 32 + ln;
    const bool lane0 = ln == 0;
    const int lrow0 = warp * 16 + g;
    const int grow0 = rb * 128 + lrow0;
    const uint32_t res = base + OFF_RES, trow = res + wg * 8192 + frag_offset(warp);
    uint32_t xr[32];
    uint4 sv[4], own;
    uint32_t* sp[4];
#pragma unroll
    for (int k = 0; k < 4; k++) sp[k] = g_stats + ((((tq >> 1) * 4 + k) ^ cj) * SEQ + grow0 + (tq & 1) * 8) * 4;
    {
      const uint64_t da = make_desc(base + wg * 8192, 16, 1024), db = make_desc(base, 8192, 1024);
      constexpr int U = UNIT / 16;
#define HALF_STAGE(acc, xu, wu) _Pragma("unroll") for (int kk = 0; kk < 4; kk++) mma_ss<1>(acc, da + (xu) * U + kk * 2, db + (wu) * U + kk * 128, 1)
      PROF(10, ct == PT, 19); STAMP(0);
      cluster_arrive();
      mbar_wait(gfull, 1);
      mbar_wait(gfull + 8, 1);
      bar_sync(2 + wg, 256);
      wg_fence();
      HALF_STAGE(o, 7, 1);
      HALF_STAGE(o, 8, 3);
      wg_commit();
      STAMP(16);
      mbar_wait(gfull + 16, 1);
      STAMP(17);
      wg_fence();
      HALF_STAGE(o, 6, 11);
      wg_commit();
      bar_arrive(3 - wg, 256);
      mbar_wait(bar_par, 0);
      uint32_t* xo = g_xch + ((size_t)b * 8 * 256 + ct) * 4;
      const uint32_t* xi = g_xch + ((size_t)(b ^ 2) * 8 * 256 + ct) * 4;
      const uint32_t par1 = (~lds1(par + PAR_CONST + 4) & 1) << 16;
      uint32_t ga[16];
      uint4 bw[8];
#define LOAD_PAR _Pragma("unroll") for (int i = 0; i < 8; i++) {                                                               \
        ga[2 * i] = lds1(par + PAR_T2 + i * 128 + tq * 16 + 12); ga[2 * i + 1] = lds1(par + PAR_T2 + i * 128 + 64 + tq * 16 + 12); \
        bw[i] = lds4(par + PAR_T1 + i * 64 + tq * 16);                                                                          \
        if (!(g & 1)) { bw[i].x = 0x3f803f80u; bw[i].y = 0x3f803f80u; }                                                         \
      }
      if (PPOS == 0) LOAD_PAR
      wg_wait<1>();
      mbar_arrive_pred(bar_rel, lane0);
      wg_wait<0>();
      keep(o);
      mbar_arrive_pred(bar_ring, lane0);
      PROF(8, ct == PT, 20); STAMP(1);
#define SEND(i) st_b128(xo + (i) * 1024, (pack_bf(o[8 * (i)], o[8 * (i) + 1]) & ~0x10000u) | par1, pack_bf(o[8 * (i) + 2], o[8 * (i) + 3]), \
                        pack_bf(o[8 * (i) + 4], o[8 * (i) + 5]), pack_bf(o[8 * (i) + 6], o[8 * (i) + 7]))
#pragma unroll
      for (int i = 0; i < NS1; i++) SEND(i);
      PROF(8, ct == PT, 21); STAMP(2);
      bar_sync(2 + wg, 256);
      wg_fence();
      HALF_STAGE(s, 7, 0);
      HALF_STAGE(s, 8, 2);
      HALF_STAGE(s, 6, 10);
      wg_commit();
      bar_arrive(3 - wg, 256);
      STAMP(18);
      mbar_wait(gfull + 24, 1);
#pragma unroll
      for (int i = NS1; i < 8; i++) SEND(i);
      uint4 v[8];
#pragma unroll
      for (int i = 0; i < 4; i++) v[i] = ld_b128(xi + i * 1024);
      if (PPOS == 1) LOAD_PAR
      STAMP(19);
      mbar_wait(bar_xres, 0);
      wg_wait<0>();
      mbar_arrive_pred(bar_ring + 8, lane0);
      bar_sync(2 + wg, 256);
      STAMP(20);
#pragma unroll
      for (int i = 4; i < 8; i++) v[i] = ld_b128(xi + i * 1024);
      mbar_wait(bar_xres, 0);
      wg_fence();
      HALF_STAGE(s, 9, 4);
      wg_commit();
      mbar_wait(bar_rx, 0);
      wg_fence();
      HALF_STAGE(s, 1, 5);
      wg_commit();
      bar_arrive(3 - wg, 256);
      STAMP(21);
      wg_wait<0>();
      keep(s);
      mbar_arrive_pred(bar_ring + 16, lane0);
      PROF(10, ct == PT, 23); STAMP(4);
#pragma unroll
      for (int i = 0; i < 16; i += 2) ldmatrix4((trow ^ ((i & 7) << 4)) + (i >> 3) * 16384, xr[2 * i], xr[2 * i + 1], xr[2 * i + 2], xr[2 * i + 3]);
      if (PPOS == 2) LOAD_PAR
      uint32_t pk[32];
      pack_p(s, pk);
      keep(pk);
      {
        uint32_t n = 0, miss;
        do {
          miss = 0;
#pragma unroll
          for (int i = 0; i < 8; i++) miss |= v[i].x ^ par1;
          miss = __any_sync(0xffffffffu, miss & 0x10000u);
          if (miss) {
#pragma unroll
            for (int i = 0; i < 8; i++)
              asm volatile("{ .reg .pred p; .reg .b32 t; xor.b32 t, %0, %5; and.b32 t, t, 0x10000; setp.ne.u32 p, t, 0;\n"
                           "@p ld.relaxed.gpu.global.v4.u32 {%0, %1, %2, %3}, [%4]; }"
                           : "+r"(v[i].x), "+r"(v[i].y), "+r"(v[i].z), "+r"(v[i].w) : "l"(xi + i * 1024), "r"(par1) : "memory");
          }
          watchdog(n);
        } while (miss);
      }
      PROF(8, ct == PT, 22); STAMP(3);
#pragma unroll
      for (int k = 0; k < 4; k++) sv[k] = ESV ? ld_b128(sp[k]) : make_uint4(0, 0, 0, 0);
      float ds[4] = {0.f, 0.f, 0.f, 0.f}, dl[4] = {0.f, 0.f, 0.f, 0.f}, q0[4] = {0.f, 0.f, 0.f, 0.f}, q1[4] = {0.f, 0.f, 0.f, 0.f};
#pragma unroll
      for (int i = 0; i < 8; i++) {
        const uint32_t u0 = hfma2(ga[2 * i], hadd2(pk[4 * i], v[i].x & ~0x10000u), xr[4 * i]);
        const uint32_t u1 = hfma2(ga[2 * i], hadd2(pk[4 * i + 1], v[i].y), xr[4 * i + 1]);
        const uint32_t u2 = hfma2(ga[2 * i + 1], hadd2(pk[4 * i + 2], v[i].z), xr[4 * i + 2]);
        const uint32_t u3 = hfma2(ga[2 * i + 1], hadd2(pk[4 * i + 3], v[i].w), xr[4 * i + 3]);
        xr[4 * i] = u0; xr[4 * i + 1] = u1; xr[4 * i + 2] = u2; xr[4 * i + 3] = u3;
        mma16816(ds, u0, u1, u2, u3, bw[i].x, bw[i].y);
        mma16816(dl, u0, u1, u2, u3, bw[i].z, bw[i].w);
        mma16816(q0, u0, u1, u2, u3, u0, u2);
        mma16816(q1, u0, u1, u2, u3, u1, u3);
      }
      const float sqa = __shfl_sync(0xffffffffu, (g & 1) ? q0[1] : q0[0], g * 4 + (g >> 1));
      const float sqb = __shfl_sync(0xffffffffu, (g & 1) ? q1[3] : q1[2], g * 4 + (g >> 1));
      own = (tq & 1) ? make_uint4(__float_as_uint(ds[2]), __float_as_uint(sqb), __float_as_uint(ds[3] + dl[3]), tag)
                                 : make_uint4(__float_as_uint(ds[0]), __float_as_uint(sqa), __float_as_uint(ds[1] + dl[1]), tag);
      if (tq < 2) st_b128(sp[0], own.x, own.y, own.z, own.w);
    }
    PROF(8, ct == PT, 29); STAMP(5);
    uint32_t mm, ih, il;
    float rbest;
    uint32_t wf[128];
    const uint32_t frow = (ln & 7) + (ln >> 4) * 8;
    const uint32_t wfo = base + (warp & 1) * 8192 + frow * 64 + ((((ln >> 3) & 1) ^ ((frow >> 1) & 3)) << 4);
#define LOAD_WF(m) _Pragma("unroll") for (int f = 0; f < 16; f++) {                                                   \
      const int r = ((f >> 1) * 4 + (m) * 2 + (f & 1)) * 4;                                                           \
      ldmatrix4t(((wfo + unit_of((m) ? FT_U : FT_G, warp >> 1)) ^ ((f & 1) * 32)) + (f >> 1) * 1024, wf[r], wf[r + 1], wf[r + 2], wf[r + 3]); \
    }
    bool early, wait1;
    {
#pragma unroll
      for (int i = 0; i < 16; i += 2) stmatrix4((trow ^ ((i & 7) << 4)) + (i >> 3) * 16384, xr[2 * i], xr[2 * i + 1], xr[2 * i + 2], xr[2 * i + 3]);
      const uint4 cst = lds4(par + PAR_CONST);
      const float A1 = __uint_as_float(cst.x), A2 = __uint_as_float(cst.z);
      uint32_t n = 0;
      early = false; wait1 = false;
#pragma unroll 1
      while (true) {
        uint32_t miss;
        asm volatile("{ .reg .pred p0, p1, p2, p3; .reg .b64 u, v; .reg .b128 w;\n"
                     "setp.ge.u32 p0, %22, 2; setp.ne.and.u32 p0, %4, %21, p0; setp.ne.u32 p1, %8, %21; setp.ne.u32 p2, %12, %21; setp.ne.u32 p3, %16, %21;\n"
                     "@p0 ld.relaxed.gpu.global.v4.u32 {%1, %2, %3, %4}, [%17];\n"
                     "@p1 ld.relaxed.gpu.global.v4.u32 {%5, %6, %7, %8}, [%18];\n"
                     "@p2 ld.relaxed.gpu.global.v4.u32 {%9, %10, %11, %12}, [%19];\n"
                     "@p3 ld.relaxed.gpu.global.v4.u32 {%13, %14, %15, %16}, [%20];\n"
                     "or.pred p0, p0, p1; or.pred p2, p2, p3; or.pred p0, p0, p2; vote.sync.any.pred p0, p0, 0xffffffff; selp.u32 %0, 1, 0, p0; }"
                     : "=r"(miss), "+r"(sv[0].x), "+r"(sv[0].y), "+r"(sv[0].z), "+r"(sv[0].w), "+r"(sv[1].x), "+r"(sv[1].y), "+r"(sv[1].z), "+r"(sv[1].w),
                       "+r"(sv[2].x), "+r"(sv[2].y), "+r"(sv[2].z), "+r"(sv[2].w), "+r"(sv[3].x), "+r"(sv[3].y), "+r"(sv[3].z), "+r"(sv[3].w)
                     : "l"(sp[0]), "l"(sp[1]), "l"(sp[2]), "l"(sp[3]), "r"(tag), "r"(tq) : "memory");
        if (!miss) break;
        wait1 = true;
        if (!early && (b >= NFFN || __all_sync(0xffffffffu, mbar_test(bar_box + (warp >> 1) * 8, 0)))) {
          early = true;
          LOAD_WF(0);
          __syncwarp();
          mbar_arrive_pred(bar_gate, lane0);
        }
        watchdog(n);
      }
      const uint4 v0 = tq < 2 ? own : sv[0], v1 = sv[1], v2 = sv[2], v3 = sv[3];
      PROF(8, ct == PT, 30); STAMP(6);
      float su = (__uint_as_float(v0.x) + __uint_as_float(v1.x)) + (__uint_as_float(v2.x) + __uint_as_float(v3.x));
      float sq = (__uint_as_float(v0.y) + __uint_as_float(v1.y)) + (__uint_as_float(v2.y) + __uint_as_float(v3.y));
      float dt = (__uint_as_float(v0.z) + __uint_as_float(v1.z)) + (__uint_as_float(v2.z) + __uint_as_float(v3.z));
      su += __shfl_xor_sync(0xffffffffu, su, 2); sq += __shfl_xor_sync(0xffffffffu, sq, 2); dt += __shfl_xor_sync(0xffffffffu, dt, 2);
      const float m = su * (1.f / DM);
      float mb, sd;
      ln_scalars(m, fmaxf(sq * (1.f / DM) - m * m, 0.f), mb, sd);
      const float inv = rcp(sd);
      rbest = (dt - mb * A1) * inv + A2;
      mm = pack_bf(mb, mb);
      ih = pack_bf(inv, inv);
      const float lo = inv - bf_lo(ih);
      il = pack_bf(lo, lo);
    }
    int ibest;
    {
      const uint32_t bits = __float_as_uint(rbest);
      const uint32_t key = (((int)bits < 0 ? ~bits : bits | 0x80000000u) & ~0x1ffu) | ((127 - lrow0 - (tq & 1) * 8) << 2) | tag;
      sts1(par + PAR_RED + warp * 4, __reduce_max_sync(0xffffffffu, key));
      PROF(8, ct == PT, 38); STAMP(7);
      uint32_t waited;
      asm volatile("{ .reg .pred p, q; setp.ne.u32 p, %1, 0; barrier.cta.red.or.pred q, 1, 256, p; selp.u32 %0, 1, 0, q; }" : "=r"(waited) : "r"((uint32_t)(wait1 && (wg || CW0))) : "memory");
      const uint4 ka = lds4(par + PAR_RED), kb = lds4(par + PAR_RED + 16);
      const uint32_t k2 = max(max(max(ka.x, ka.y), max(ka.z, ka.w)), max(max(kb.x, kb.y), max(kb.z, kb.w)));
      if (ct == 0 && ((cj & CWM) == 0 || (CWL && !waited))) st_relaxed(g_cand + rb, k2);
      ibest = 127 - ((k2 >> 2) & 127);
    }
    PROF(8, ct == PT, 39); STAMP(8);
    if ((ibest >> 4) == warp) {
      const int src = (ibest & 7) * 4 + ((ibest >> 3) & 1), ch = g * 2;
      const uint32_t cm = __shfl_sync(0xffffffffu, mm, src), ch_ = __shfl_sync(0xffffffffu, ih, src), cl = __shfl_sync(0xffffffffu, il, src);
      const uint32_t xa = res + (ch >> 3) * 16384 + ibest * 128 + (((ch & 7) ^ (ibest & 7)) << 4) + tq * 4;
      const uint32_t x0 = lds1(xa), x1 = lds1(xa ^ 16);
      const uint2 p0 = lds2(par + PAR_T2 + ch * 64 + tq * 16), p1 = lds2(par + PAR_T2 + ch * 64 + 64 + tq * 16);
      uint32_t* dst = g_row + rb * 2 * DM + cj * 128 + ln * 4;
      st_pairs(dst, ln_mod(x0, cm, ch_, cl, p0.x, p0.y), ln_mod(x1, cm, ch_, cl, p1.x, p1.y), tag);
      st_pairs(dst + DM, x0, x1, tag);
      __syncwarp();
    }
    PROF(8, ct == PT, 37); STAMP(9);
    uint32_t wd[64];
    const uint32_t wda = base + unit_of(FT_D, warp >> 1) + (warp & 1) * 8192 + frow * 128 + ((((ln >> 3) & 1) ^ (ln & 7)) << 4);
#define LOAD_WD(f) ldmatrix4t((wda ^ ((((f) >> 1) & 3) * 32)) + ((f) >> 3) * 4096 + ((f) & 1) * 2048, wd[4 * (f)], wd[4 * (f) + 1], wd[4 * (f) + 2], wd[4 * (f) + 3])
    if (!early) {
      if (b < NFFN) mbar_wait(bar_box + (warp >> 1) * 8, 0);
      LOAD_WF(0);
      __syncwarp();
      mbar_arrive_pred(bar_gate, lane0);
    }
    if (b < NFFN) {
      const uint32_t own = base + unit_of(FT_G, warp >> 1) + (warp & 1) * 8192;
      mbar_wait(bar_box + (4 + (warp >> 1)) * 8, 0);
      LOAD_WF(1);
      uint32_t* const ydst = g_ypart + ((size_t)(warp * 16 + tq * 2) * NFFN + b) * 8 + g;
      PROF(8, ct == PT, 31); STAMP(10);
      mbar_wait(bar_box + (8 + (warp >> 1)) * 8, 0);
#pragma unroll
      for (int f = 0; f < WDE; f++) LOAD_WD(f);
      STAMP(11);
      mbar_wait(bar_sel, 0);
      PROF(8, ct == PT, 33); STAMP(12);
      float d[8][4];
#pragma unroll
      for (int i = 0; i < 4; i++) { d[i][0] = 0.f; d[i][1] = 0.f; d[i][2] = 0.f; d[i][3] = 0.f; }
#pragma unroll
      for (int ks = 0; ks < 8; ks++) {
        const uint2 hb = lds2(own + 256 + ks * 32 + tq * 8);
#pragma unroll
        for (int mt = 0; mt < 4; mt++) {
          const int r = ks * 16 + mt * 4;
          mma16816(d[mt], wf[r], wf[r + 1], wf[r + 2], wf[r + 3], hb.x, hb.y);
        }
      }
      sts2(own + (tq * 8 + g) * 8, __float_as_uint((tq & 2) ? ((tq & 1) ? d[1][2] : d[1][0]) : ((tq & 1) ? d[0][2] : d[0][0])),
           __float_as_uint((tq & 2) ? ((tq & 1) ? d[3][2] : d[3][0]) : ((tq & 1) ? d[2][2] : d[2][0])));
      bar_sync(1, 256);
      uint32_t ab[4];
      {
        float G = 0.f, U = 0.f;
        uint2 pv[8];
#pragma unroll
        for (int w8 = 0; w8 < 8; w8++) pv[w8] = lds2(base + ln * 8 + ((FT_G >> (w8 >> 1) * 4) & 15) * UNIT + (w8 & 1) * 8192);
#pragma unroll
        for (int w8 = 0; w8 < 8; w8 += 2) {
          G += __uint_as_float(pv[w8].x) + __uint_as_float(pv[w8 + 1].x);
          U += __uint_as_float(pv[w8].y) + __uint_as_float(pv[w8 + 1].y);
        }
#pragma unroll
        for (int f = WDE; f < 16; f++) LOAD_WD(f);
        const float act = rbf(silu_f(rbf(G))) * rbf(U);
        const uint32_t pk = pack_bf(act, __shfl_down_sync(0xffffffffu, act, 1));
#pragma unroll
        for (int i = 0; i < 4; i++) ab[i] = __shfl_sync(0xffffffffu, pk, i * 8 + tq * 2);
      }
      PROF(8, ct == PT, 34); STAMP(13);
#pragma unroll
      for (int mt = 0; mt < 8; mt++) {
        d[mt][0] = 0.f; d[mt][1] = 0.f; d[mt][2] = 0.f; d[mt][3] = 0.f;
        mma16816(d[mt], wd[mt * 8], wd[mt * 8 + 1], wd[mt * 8 + 2], wd[mt * 8 + 3], ab[0], ab[1]);
        mma16816(d[mt], wd[mt * 8 + 4], wd[mt * 8 + 5], wd[mt * 8 + 6], wd[mt * 8 + 7], ab[2], ab[3]);
      }
#pragma unroll
      for (int i = 0; i < 4; i++) {
        const int m4 = (i >> 1) * 4, e = (i & 1) * 2;
        const float y = (tq & 2) ? ((tq & 1) ? d[m4 + 3][e] : d[m4 + 2][e]) : ((tq & 1) ? d[m4 + 1][e] : d[m4][e]);
        st_relaxed(ydst + (m4 * 2 + (i & 1)) * NFFN * 8, tagf(y, tag));
      }
      PROF(8, ct == PT, 35); STAMP(14);
    }
    mbar_wait(bar_sel, 0);
    mbar_arrive_pred(bar_win, ct == 0);
    const int iwin = lds1(par + PAR_CONST + 60) & 0x7ff;
    {
      const uint32_t mm0 = __shfl_sync(0xffffffffu, mm, ln & ~1), mm1 = __shfl_sync(0xffffffffu, mm, ln | 1);
      const uint32_t ih0 = __shfl_sync(0xffffffffu, ih, ln & ~1), ih1 = __shfl_sync(0xffffffffu, ih, ln | 1);
      const uint32_t il0 = __shfl_sync(0xffffffffu, il, ln & ~1), il1 = __shfl_sync(0xffffffffu, il, ln | 1);
      const bool mine = (iwin >> 4) == rb * 8 + warp;
#pragma unroll 1
      for (int hf = 0; hf < 2; hf++) {
        uint32_t x[16];
#pragma unroll
        for (int i = 0; i < 8; i += 2) ldmatrix4((trow ^ (i << 4)) + hf * 16384, x[2 * i], x[2 * i + 1], x[2 * i + 2], x[2 * i + 3]);
#pragma unroll
        for (int i = 0; i < 8; i++) {
          const uint4 pv = lds4(par + PAR_T2 + (hf * 8 + i) * 64 + tq * 16);
          x[2 * i] = hadd2(x[2 * i], hmul2(pv.z, ln_mod(x[2 * i], mm0, ih0, il0, pv.x, pv.y)));
          x[2 * i + 1] = hadd2(x[2 * i + 1], hmul2(pv.z, ln_mod(x[2 * i + 1], mm1, ih1, il1, pv.x, pv.y)));
        }
        if (mine) {
          uint32_t* dst = reinterpret_cast<uint32_t*>(P.out + (size_t)grow0 * DM + cj * 128 + hf * 64) + tq;
#pragma unroll
          for (int i = 0; i < 8; i++) {
            if (grow0 != iwin) dst[i * 4] = x[2 * i];
            if (grow0 + 8 != iwin) dst[i * 4 + 4 * DM] = x[2 * i + 1];
          }
        } else {
#pragma unroll
          for (int i = 0; i < 8; i += 2) stmatrix4((trow ^ (i << 4)) + hf * 16384, x[2 * i], x[2 * i + 1], x[2 * i + 2], x[2 * i + 3]);
          fence_async_smem();
          __syncwarp();
          if (elect_one()) {
            tma2d_store(&maps.out, res + hf * 16384 + warp * 2048, cj * 128 + hf * 64, rb * 128 + warp * 16);
            asm volatile("cp.async.bulk.commit_group;" ::: "memory");
          }
        }
      }
      asm volatile("cp.async.bulk.wait_group.read 0;" ::: "memory");
    }
    PROF(8, ct == PT, 11); STAMP(15);
    cluster_wait();
  }
}

typedef CUresult (*EncodeFn)(CUtensorMap*, CUtensorMapDataType, cuuint32_t, void*, const cuuint64_t*, const cuuint64_t*,
                             const cuuint32_t*, const cuuint32_t*, CUtensorMapInterleave, CUtensorMapSwizzle,
                             CUtensorMapL2promotion, CUtensorMapFloatOOBfill);

void map2d(EncodeFn enc, CUtensorMap* m, const void* p, uint64_t rows, uint64_t cols, uint32_t brows) {
  cuuint64_t dims[2] = {cols, rows}, strides[1] = {cols * 2};
  cuuint32_t box[2] = {64, brows}, es[2] = {1, 1};
  enc(m, CU_TENSOR_MAP_DATA_TYPE_BFLOAT16, 2, const_cast<void*>(p), dims, strides, box, es, CU_TENSOR_MAP_INTERLEAVE_NONE,
      CU_TENSOR_MAP_SWIZZLE_128B, CU_TENSOR_MAP_L2_PROMOTION_L2_256B, CU_TENSOR_MAP_FLOAT_OOB_FILL_NONE);
}
void map2d_narrow(EncodeFn enc, CUtensorMap* m, const void* p, uint64_t rows, uint64_t cols, uint32_t brows) {
  cuuint64_t dims[2] = {cols, rows}, strides[1] = {cols * 2};
  cuuint32_t box[2] = {32, brows}, es[2] = {1, 1};
  enc(m, CU_TENSOR_MAP_DATA_TYPE_BFLOAT16, 2, const_cast<void*>(p), dims, strides, box, es, CU_TENSOR_MAP_INTERLEAVE_NONE,
      CU_TENSOR_MAP_SWIZZLE_64B, CU_TENSOR_MAP_L2_PROMOTION_L2_64B, CU_TENSOR_MAP_FLOAT_OOB_FILL_NONE);
}
void map3d(EncodeFn enc, CUtensorMap* m, const void* p, uint64_t rows, uint64_t cols, uint32_t brows, uint32_t nch) {
  cuuint64_t dims[3] = {64, rows, cols / 64}, strides[2] = {cols * 2, 128};
  cuuint32_t box[3] = {64, brows, nch}, es[3] = {1, 1, 1};
  enc(m, CU_TENSOR_MAP_DATA_TYPE_BFLOAT16, 3, const_cast<void*>(p), dims, strides, box, es, CU_TENSOR_MAP_INTERLEAVE_NONE,
      CU_TENSOR_MAP_SWIZZLE_128B, CU_TENSOR_MAP_L2_PROMOTION_L2_256B, CU_TENSOR_MAP_FLOAT_OOB_FILL_NONE);
}

}

extern "C" void kernel_launch(void* const* d_in, const int* in_sizes, int n_in, void* d_out, int out_size) {
  (void)in_sizes; (void)n_in; (void)out_size;
  static EncodeFn enc = nullptr;
  if (!enc) {
    void* fn = nullptr;
    cudaDriverEntryPointQueryResult st;
    cudaGetDriverEntryPoint("cuTensorMapEncodeTiled", &fn, cudaEnableDefault, &st);
    enc = (EncodeFn)fn;
    cudaFuncSetAttribute(fused_kernel, cudaFuncAttributeMaxDynamicSharedMemorySize, SMEM_BYTES);
  }
  Maps maps;
  map2d(enc, &maps.x, d_in[0], SEQ, DM, 128);
  map2d(enc, &maps.out, d_out, SEQ, DM, 16);
  map3d(enc, &maps.wq, d_in[3], DM, NQ, 64, 2);
  map3d(enc, &maps.k, d_in[1], 4 * SK, 128, 128, 1);
  map3d(enc, &maps.v, d_in[2], 4 * SK, 128, 128, 1);
  map3d(enc, &maps.wo, d_in[4], NQ, DM, 64, 2);
  map2d_narrow(enc, &maps.wg, d_in[7], DM, FF, 256);
  map2d_narrow(enc, &maps.wu, d_in[8], DM, FF, 256);
  map3d(enc, &maps.wd, d_in[9], FF, DM, 32, 4);
  map2d_narrow(enc, &maps.wm, d_in[11], DM, NMOD, 256);
  Ptrs p;
  p.x = (const __nv_bfloat16*)d_in[0];
  p.w_r = (const __nv_bfloat16*)d_in[6];
  p.w_gate = (const __nv_bfloat16*)d_in[7];
  p.w_up = (const __nv_bfloat16*)d_in[8];
  p.w_down = (const __nv_bfloat16*)d_in[9];
  p.c = (const __nv_bfloat16*)d_in[10];
  p.w_mod = (const __nv_bfloat16*)d_in[11];
  p.out = (__nv_bfloat16*)d_out;
  fused_kernel<<<NMAIN + NHELP, 384, SMEM_BYTES>>>(maps, p);
}
```

```cpp
#include <cuda_runtime.h>
#include <cuda_bf16.h>
#include <cuda.h>
#include <stdint.h>
#include <type_traits>

#define HD 2
#define HDX 2
#define XF 4
#define XE 32
#define XR 0
#define NRS 8
#define FPACE 3
#define GOST 20
#define WB 3
#define WN 24
#define RES0 17
#define RES1 20
#define HU 32
#define NS1 6
#define PG0 0
#define PSL 0
#define CWM 7
#define WDE 16
#define CWL 1
#define CW0 0
#define ESV 1
#define PPOS 1
#define FB0 0
#define FB2 8
#define OPS 8192
#define OFL 0
#define ODS 8
#define PORD 0
#define MODUL hfma2
#define VREL 7
#define E0 3

namespace {

constexpr int SEQ = 2048, DM = 1024, NQ = 4096, SK = 2048, WIN = 512, FF = 3584, NMOD = 6144;
constexpr int NMAIN = 128, NHELP = 4, NFFN = 112;
constexpr int NSLOT = 4, SLOT_BYTES = 32768, UNIT = 16384, GST_BYTES = 3 * UNIT;
constexpr uint32_t XT1 = 0xDCBA, XT2 = 0x9687;
constexpr uint32_t WT0 = 0xA741, WT1 = 0x7420, WT2 = 0x4A20;
constexpr uint32_t AT0 = WT1, AT1 = WT2;
constexpr uint32_t QT = 0xDC9696DC;
constexpr int OFF_STAGE = 12 * UNIT;
constexpr uint32_t FT_G = 0x07B3, FT_U = 0xA628, FT_D = 0x5149;
constexpr int OFF_RES = 12 * UNIT;
constexpr int OFF_PAR = 14 * UNIT;
constexpr int OFF_BAR = OFF_PAR + 2528;
constexpr int SMEM_BYTES = OFF_BAR + 544;
static_assert(SMEM_BYTES <= 232448, "smem");

constexpr int PAR_T1 = 0;
constexpr int PAR_T2 = 512;
constexpr int PAR_CONST = 1536;
constexpr int PAR_RED = 1600;
constexpr int PAR_SINK = 2176;

struct Maps {
  CUtensorMap x, wq, k, v, wo, wg, wu, wd, wm, out;
};
struct Ptrs {
  const __nv_bfloat16 *x, *w_r, *c, *w_mod, *w_gate, *w_up, *w_down;
  __nv_bfloat16* out;
};

__device__ __align__(1024) uint8_t g_act[16 * 80 * UNIT];
__device__ __align__(128) uint32_t g_mod[NMOD];
__device__ __align__(128) uint32_t g_modp[2 * 2 * DM];
__device__ __align__(128) uint32_t g_ln1[SEQ * 4];
__device__ __align__(128) uint32_t g_cnt_h[16 * 32];
__device__ __align__(128) uint32_t g_cnt_o[128 * 32];
__device__ __align__(128) uint32_t g_xch[NMAIN * 8 * 256 * 4];
__device__ __align__(128) uint32_t g_stats[8 * SEQ * 4];
__device__ __align__(128) uint32_t g_cand[32];
__device__ __align__(128) uint32_t g_row[16 * 2 * DM];
__device__ __align__(128) uint32_t g_ypart[NMAIN * NFFN * 8];
__device__ uint32_t g_epoch;

__device__ __forceinline__ uint32_t fresh_lane() { uint32_t l; asm volatile("mov.u32 %0, %%laneid;" : "=r"(l)); return l; }
__device__ __forceinline__ uint32_t frag_offset(int warp) {
  const uint32_t l = fresh_lane();
  return ((warp & 3) * 16 + (l & 15)) * 128 + (((l >> 4) ^ (l & 7)) << 4);
}
__device__ __forceinline__ bool elect_one() {
  uint32_t p;
  asm volatile("{ .reg .pred q; elect.sync _|q, 0xffffffff; selp.u32 %0, 1, 0, q; }" : "=r"(p));
  return p;
}
__device__ __forceinline__ uint32_t smem_u32(const void* p) { return (uint32_t)__cvta_generic_to_shared(p); }
__device__ __forceinline__ void mbar_init(uint32_t bar, uint32_t cnt) {
  asm volatile("mbarrier.init.shared::cta.b64 [%0], %1;" ::"r"(bar), "r"(cnt) : "memory");
}
__device__ __forceinline__ void mbar_expect_tx(uint32_t bar, uint32_t bytes) {
  asm volatile("mbarrier.arrive.expect_tx.shared::cta.b64 _, [%0], %1;" ::"r"(bar), "r"(bytes) : "memory");
}
__device__ __forceinline__ void mbar_arrive(uint32_t bar) {
  asm volatile("mbarrier.arrive.shared::cta.b64 _, [%0];" ::"r"(bar) : "memory");
}
__device__ __forceinline__ void mbar_arrive_pred(uint32_t bar, bool p) {
  asm volatile("{ .reg .pred p; setp.ne.b32 p, %1, 0; @p mbarrier.arrive.shared::cta.b64 _, [%0]; }" ::"r"(bar), "r"((int)p) : "memory");
}
__device__ __forceinline__ void mbar_arrive_cl(uint32_t bar, uint32_t off, bool p = true) {
  asm volatile("{ .reg .pred p, q; .reg .b32 a; setp.ne.b32 q, %2, 0; setp.ne.and.b32 p, %0, 0, q; add.u32 a, %0, %1; @p mbarrier.arrive.shared::cluster.b64 _, [a]; }"
               ::"r"(bar), "r"(off), "r"((int)p) : "memory");
}
__device__ __forceinline__ uint32_t mapa(uint32_t addr, uint32_t cta) {
  uint32_t r; asm("mapa.shared::cluster.u32 %0, %1, %2;" : "=r"(r) : "r"(addr), "r"(cta)); return r;
}
__device__ __forceinline__ void cluster_arrive() { asm volatile("barrier.cluster.arrive.relaxed.aligned;" ::: "memory"); }
__device__ __forceinline__ void cluster_wait() { asm volatile("barrier.cluster.wait.aligned;" ::: "memory"); }
__device__ __forceinline__ void watchdog(uint32_t& n) {
}
__device__ __forceinline__ void mbar_wait(uint32_t bar, uint32_t parity) {
  asm volatile("{\n.reg .pred p;\nWAIT_%=:\nmbarrier.try_wait.parity.shared::cta.b64 p, [%0], %1;\n@!p bra WAIT_%=;\n}" ::"r"(bar), "r"(parity) : "memory");
}
__device__ __forceinline__ bool mbar_test(uint32_t bar, uint32_t parity) {
  uint32_t ok;
  asm volatile("{\n.reg .pred p;\nmbarrier.test_wait.parity.shared::cta.b64 p, [%1], %2;\nselp.u32 %0, 1, 0, p;\n}" : "=r"(ok) : "r"(bar), "r"(parity) : "memory");
  return ok;
}
__device__ __forceinline__ uint64_t l2_stream() {
  uint64_t f; asm("createpolicy.fractional.L2::evict_first.b64 %0, 1.0;" : "=l"(f)); return f;
}
__device__ __forceinline__ void tma2d(uint32_t dst, const CUtensorMap* m, int c0, int c1, uint32_t bar) {
  asm volatile("cp.async.bulk.tensor.2d.shared::cluster.global.mbarrier::complete_tx::bytes.L2::cache_hint [%0], [%1, {%3, %4}], [%2], %5;"
               ::"r"(dst), "l"(m), "r"(bar), "r"(c0), "r"(c1), "l"(l2_stream()) : "memory");
}
__device__ __forceinline__ void bulk_load(uint32_t dst, const void* src, uint32_t bytes, uint32_t bar) {
  asm volatile("cp.async.bulk.shared::cluster.global.mbarrier::complete_tx::bytes [%0], [%1], %2, [%3];" ::"r"(dst), "l"(src), "r"(bytes), "r"(bar) : "memory");
}
__device__ __forceinline__ void bulk_load_stream(uint32_t dst, const void* src, uint32_t bytes, uint32_t bar) {
  asm volatile("cp.async.bulk.shared::cluster.global.mbarrier::complete_tx::bytes.L2::cache_hint [%0], [%1], %2, [%3], %4;"
               ::"r"(dst), "l"(src), "r"(bytes), "r"(bar), "l"(l2_stream()) : "memory");
}
__device__ __forceinline__ void tma2d_store(const CUtensorMap* m, uint32_t src, int c0, int c1) {
  asm volatile("cp.async.bulk.tensor.2d.global.shared::cta.bulk_group [%0, {%2, %3}], [%1];" ::"l"(m), "r"(src), "r"(c0), "r"(c1) : "memory");
}
__device__ __forceinline__ void bulk_store(void* dst, uint32_t src, uint32_t bytes) {
  asm volatile("cp.async.bulk.global.shared::cta.bulk_group [%0], [%1], %2;" ::"l"(dst), "r"(src), "r"(bytes) : "memory");
}
__device__ __forceinline__ uint32_t unit_of(uint32_t table, uint32_t i) { return ((table >> (i * 4)) & 15) * UNIT; }
__device__ __forceinline__ void tma3d(uint32_t dst, const CUtensorMap* m, int c0, int c1, int c2, uint32_t bar) {
  asm volatile("cp.async.bulk.tensor.3d.shared::cluster.global.mbarrier::complete_tx::bytes.L2::cache_hint [%0], [%1, {%3, %4, %5}], [%2], %6;"
               ::"r"(dst), "l"(m), "r"(bar), "r"(c0), "r"(c1), "r"(c2), "l"(l2_stream()) : "memory");
}
template <bool STREAM>
__device__ __forceinline__ void tma3d_mc(uint32_t dst, const CUtensorMap* m, int c0, int c1, int c2, uint32_t bar) {
  if (STREAM)
    asm volatile("cp.async.bulk.tensor.3d.shared::cluster.global.mbarrier::complete_tx::bytes.multicast::cluster.L2::cache_hint [%0], [%1, {%3, %4, %5}], [%2], %6, %7;"
                 ::"r"(dst), "l"(m), "r"(bar), "r"(c0), "r"(c1), "r"(c2), "h"((uint16_t)3), "l"(l2_stream()) : "memory");
  else
    asm volatile("cp.async.bulk.tensor.3d.shared::cluster.global.mbarrier::complete_tx::bytes.multicast::cluster [%0], [%1, {%3, %4, %5}], [%2], %6;"
                 ::"r"(dst), "l"(m), "r"(bar), "r"(c0), "r"(c1), "r"(c2), "h"((uint16_t)3) : "memory");
}
__device__ __forceinline__ void prefetch_map(const CUtensorMap* m) {
  asm volatile("prefetch.tensormap [%0];" ::"l"(m) : "memory");
}
__device__ __forceinline__ void fence_async() { asm volatile("fence.proxy.async.global;" ::: "memory"); }
__device__ __forceinline__ void fence_async_smem() { asm volatile("fence.proxy.async.shared::cta;" ::: "memory"); }
__device__ __forceinline__ void bar_sync(int id, int n) { asm volatile("bar.sync %0, %1;" ::"r"(id), "r"(n) : "memory"); }
__device__ __forceinline__ void bar_arrive(int id, int n) { asm volatile("bar.arrive %0, %1;" ::"r"(id), "r"(n) : "memory"); }
__device__ __forceinline__ void wg_fence() { asm volatile("wgmma.fence.sync.aligned;" ::: "memory"); }
__device__ __forceinline__ void wg_commit() { asm volatile("wgmma.commit_group.sync.aligned;" ::: "memory"); }
template <int N> __device__ __forceinline__ void wg_wait() { asm volatile("wgmma.wait_group.sync.aligned %0;" ::"n"(N) : "memory"); }
__device__ __forceinline__ uint64_t make_desc(uint32_t addr, uint32_t lbo, uint32_t sbo) {
  return (uint64_t)((addr & 0x3FFFF) >> 4) | ((uint64_t)(lbo >> 4) << 16) | ((uint64_t)(sbo >> 4) << 32) | (1ull << 62);
}
__device__ __forceinline__ uint32_t ld_relaxed(const uint32_t* p) {
  uint32_t v; asm volatile("ld.relaxed.gpu.global.u32 %0, [%1];" : "=r"(v) : "l"(p) : "memory"); return v;
}
__device__ __forceinline__ uint32_t ld_acquire(const uint32_t* p) {
  uint32_t v; asm volatile("ld.acquire.gpu.global.u32 %0, [%1];" : "=r"(v) : "l"(p) : "memory"); return v;
}
__device__ __forceinline__ uint4 ld_relaxed4(const uint32_t* p) {
  uint4 v; asm volatile("ld.relaxed.gpu.global.v4.u32 {%0,%1,%2,%3}, [%4];" : "=r"(v.x), "=r"(v.y), "=r"(v.z), "=r"(v.w) : "l"(p) : "memory"); return v;
}
__device__ __forceinline__ uint2 ld_relaxed2(const uint32_t* p) {
  uint2 v; asm volatile("ld.relaxed.gpu.global.v2.u32 {%0,%1}, [%2];" : "=r"(v.x), "=r"(v.y) : "l"(p) : "memory"); return v;
}
__device__ __forceinline__ void st_relaxed(uint32_t* p, uint32_t v) {
  asm volatile("st.relaxed.gpu.global.u32 [%0], %1;" ::"l"(p), "r"(v) : "memory");
}
__device__ __forceinline__ void st_relaxed2(uint32_t* p, uint32_t a, uint32_t b) {
  asm volatile("st.relaxed.gpu.global.v2.u32 [%0], {%1,%2};" ::"l"(p), "r"(a), "r"(b) : "memory");
}
__device__ __forceinline__ void st_relaxed4(uint32_t* p, uint32_t a, uint32_t b, uint32_t c, uint32_t d) {
  asm volatile("st.relaxed.gpu.global.v4.u32 [%0], {%1,%2,%3,%4};" ::"l"(p), "r"(a), "r"(b), "r"(c), "r"(d) : "memory");
}
__device__ __forceinline__ void st_b128(uint32_t* p, uint32_t a, uint32_t b, uint32_t c, uint32_t d) {
  asm volatile("{ .reg .b64 u, v; .reg .b128 w; mov.b64 u, {%1, %2}; mov.b64 v, {%3, %4}; mov.b128 w, {u, v}; st.relaxed.gpu.global.b128 [%0], w; }"
               ::"l"(p), "r"(a), "r"(b), "r"(c), "r"(d) : "memory");
}
__device__ __forceinline__ uint4 ld_b128(const uint32_t* p) {
  uint4 r;
  asm volatile("{ .reg .b64 u, v; .reg .b128 w; ld.relaxed.gpu.global.b128 w, [%4]; mov.b128 {u, v}, w; mov.b64 {%0, %1}, u; mov.b64 {%2, %3}, v; }"
               : "=r"(r.x), "=r"(r.y), "=r"(r.z), "=r"(r.w) : "l"(p) : "memory");
  return r;
}
__device__ __forceinline__ void st_pairs(uint32_t* p, uint32_t a, uint32_t b, uint32_t tag) {
  asm volatile("{ .reg .b64 u, v; mov.b64 u, {%1, %3}; mov.b64 v, {%2, %3}; st.relaxed.gpu.global.v2.b64 [%0], {u, v}; }"
               ::"l"(p), "r"(a), "r"(b), "r"(tag) : "memory");
}
__device__ __forceinline__ uint4 ld_pairs(const uint32_t* p) {
  uint4 v;
  asm volatile("{ .reg .b64 u, v; ld.relaxed.gpu.global.v2.b64 {u, v}, [%4]; mov.b64 {%0, %1}, u; mov.b64 {%2, %3}, v; }"
               : "=r"(v.x), "=r"(v.y), "=r"(v.z), "=r"(v.w) : "l"(p) : "memory");
  return v;
}
__device__ __forceinline__ uint2 ld_pair(const uint32_t* p) {
  uint2 v;
  asm volatile("{ .reg .b64 u; ld.relaxed.gpu.global.b64 u, [%2]; mov.b64 {%0, %1}, u; }" : "=r"(v.x), "=r"(v.y) : "l"(p) : "memory");
  return v;
}
__device__ __forceinline__ void red_release(uint32_t* p, uint32_t v) {
  asm volatile("red.release.gpu.global.add.u32 [%0], %1;" ::"l"(p), "r"(v) : "memory");
}
__device__ __forceinline__ uint32_t ldg_nc1(const void* p) {
  uint32_t v;
  asm volatile("ld.global.nc.u32 %0, [%1];" : "=r"(v) : "l"(p));
  return v;
}
__device__ __forceinline__ uint4 ldg_nc4(const void* p) {
  uint4 v; asm volatile("ld.global.nc.L1::no_allocate.v4.u32 {%0,%1,%2,%3}, [%4];" : "=r"(v.x), "=r"(v.y), "=r"(v.z), "=r"(v.w) : "l"(p)); return v;
}
__device__ __forceinline__ uint4 ldg_stream4(const void* p) {
  uint4 v;
  asm volatile("ld.global.nc.L1::no_allocate.L2::cache_hint.v4.u32 {%0,%1,%2,%3}, [%4], %5;" : "=r"(v.x), "=r"(v.y), "=r"(v.z), "=r"(v.w) : "l"(p), "l"(l2_stream()));
  return v;
}
__device__ __forceinline__ void stg4(void* p, uint4 v) {
  asm volatile("st.global.v4.u32 [%0], {%1,%2,%3,%4};" ::"l"(p), "r"(v.x), "r"(v.y), "r"(v.z), "r"(v.w) : "memory");
}
__device__ __forceinline__ void wait_counter(const uint32_t* p, uint32_t target) {
  uint32_t n = 0;
  while (__any_sync(0xffffffffu, (int)(ld_acquire(p) - target) < 0)) { watchdog(n); }
}
__device__ __forceinline__ uint32_t tagf(float v, uint32_t tag) { return (__float_as_uint(v) & ~3u) | tag; }
__device__ __forceinline__ bool tag_ok(uint4 v, uint32_t tag) { return (((v.x ^ tag) | (v.y ^ tag) | (v.z ^ tag) | (v.w ^ tag)) & 3u) == 0; }
__device__ __forceinline__ float untag_sum(uint32_t a, uint32_t b) { return __uint_as_float(a & ~3u) + __uint_as_float(b & ~3u); }
__device__ __forceinline__ uint4 poll4(const uint32_t* p, uint32_t tag) {
  uint4 v = ld_relaxed4(p);
  uint32_t n = 0;
  while (!__all_sync(0xffffffffu, tag_ok(v, tag))) { v = ld_relaxed4(p); watchdog(n); }
  return v;
}
__device__ __forceinline__ float bf_lo(uint32_t v) { return __uint_as_float(v << 16); }
__device__ __forceinline__ float bf_hi(uint32_t v) { return __uint_as_float(v & 0xffff0000u); }
__device__ __forceinline__ uint32_t pack_bf(float lo, float hi) {
  uint32_t r; asm("cvt.rn.bf16x2.f32 %0, %1, %2;" : "=r"(r) : "f"(hi), "f"(lo)); return r;
}
__device__ __forceinline__ float rbf(float v) { return __uint_as_float(pack_bf(0.f, v) & 0xffff0000u); }
__device__ __forceinline__ uint32_t hmul2(uint32_t a, uint32_t b) {
  uint32_t r; asm("mul.rn.bf16x2 %0, %1, %2;" : "=r"(r) : "r"(a), "r"(b)); return r;
}
__device__ __forceinline__ uint32_t hadd2(uint32_t a, uint32_t b) {
  uint32_t r; asm("add.rn.bf16x2 %0, %1, %2;" : "=r"(r) : "r"(a), "r"(b)); return r;
}
__device__ __forceinline__ uint32_t hsub2(uint32_t a, uint32_t b) {
  uint32_t r; asm("sub.rn.bf16x2 %0, %1, %2;" : "=r"(r) : "r"(a), "r"(b)); return r;
}
__device__ __forceinline__ uint32_t hmax2(uint32_t a, uint32_t b) {
  uint32_t r; asm("max.bf16x2 %0, %1, %2;" : "=r"(r) : "r"(a), "r"(b)); return r;
}
__device__ __forceinline__ float rcp(float x) { float r; asm("rcp.approx.ftz.f32 %0, %1;" : "=f"(r) : "f"(x)); return r; }
__device__ __forceinline__ float ex2(float x) { float r; asm("ex2.approx.ftz.f32 %0, %1;" : "=f"(r) : "f"(x)); return r; }
__device__ __forceinline__ void stmatrix4(uint32_t addr, uint32_t a, uint32_t b, uint32_t c, uint32_t d) {
  asm volatile("stmatrix.sync.aligned.m8n8.x4.shared.b16 [%0], {%1,%2,%3,%4};" ::"r"(addr), "r"(a), "r"(b), "r"(c), "r"(d) : "memory");
}
__device__ __forceinline__ void ldmatrix4(uint32_t addr, uint32_t& a, uint32_t& b, uint32_t& c, uint32_t& d) {
  asm volatile("ldmatrix.sync.aligned.m8n8.x4.shared.b16 {%0,%1,%2,%3}, [%4];" : "=r"(a), "=r"(b), "=r"(c), "=r"(d) : "r"(addr) : "memory");
}
__device__ __forceinline__ void ldmatrix4t(uint32_t addr, uint32_t& a, uint32_t& b, uint32_t& c, uint32_t& d) {
  asm volatile("ldmatrix.sync.aligned.m8n8.x4.trans.shared.b16 {%0,%1,%2,%3}, [%4];" : "=r"(a), "=r"(b), "=r"(c), "=r"(d) : "r"(addr) : "memory");
}
__device__ __forceinline__ void mma16816(float (&d)[4], uint32_t a0, uint32_t a1, uint32_t a2, uint32_t a3, uint32_t b0, uint32_t b1) {
  asm volatile("mma.sync.aligned.m16n8k16.row.col.f32.bf16.bf16.f32 {%0,%1,%2,%3}, {%4,%5,%6,%7}, {%8,%9}, {%0,%1,%2,%3};"
               : "+f"(d[0]), "+f"(d[1]), "+f"(d[2]), "+f"(d[3]) : "r"(a0), "r"(a1), "r"(a2), "r"(a3), "r"(b0), "r"(b1));
}
__device__ __forceinline__ void sts1(uint32_t a, uint32_t v) { asm volatile("st.shared.u32 [%0], %1;" ::"r"(a), "r"(v) : "memory"); }
__device__ __forceinline__ uint4 lds4(uint32_t a) {
  uint4 v; asm volatile("ld.shared.v4.u32 {%0,%1,%2,%3}, [%4];" : "=r"(v.x), "=r"(v.y), "=r"(v.z), "=r"(v.w) : "r"(a) : "memory"); return v;
}
__device__ __forceinline__ uint2 lds2(uint32_t a) {
  uint2 v; asm volatile("ld.shared.v2.u32 {%0,%1}, [%2];" : "=r"(v.x), "=r"(v.y) : "r"(a) : "memory"); return v;
}
__device__ __forceinline__ uint32_t lds1(uint32_t a) {
  uint32_t v; asm volatile("ld.shared.u32 %0, [%1];" : "=r"(v) : "r"(a) : "memory"); return v;
}
__device__ __forceinline__ void sts2(uint32_t a, uint32_t x, uint32_t y) { asm volatile("st.shared.v2.u32 [%0], {%1,%2};" ::"r"(a), "r"(x), "r"(y) : "memory"); }
__device__ __forceinline__ void sts4(uint32_t a, uint4 v) {
  asm volatile("st.shared.v4.u32 [%0], {%1,%2,%3,%4};" ::"r"(a), "r"(v.x), "r"(v.y), "r"(v.z), "r"(v.w) : "memory");
}
__device__ __forceinline__ float silu_f(float v) { return __fdividef(v, 1.f + __expf(-v)); }
__device__ __forceinline__ uint32_t hfma2(uint32_t a, uint32_t b, uint32_t c) {
  uint32_t r; asm("fma.rn.bf16x2 %0, %1, %2, %3;" : "=r"(r) : "r"(a), "r"(b), "r"(c)); return r;
}
__device__ __forceinline__ void split_inv(float sd, uint32_t& ih, uint32_t& il) {
  const float inv = rcp(sd);
  ih = pack_bf(inv, inv);
  const float lo = inv - bf_lo(ih);
  il = pack_bf(lo, lo);
}
__device__ __forceinline__ uint32_t ln_norm(uint32_t x, uint32_t mean2, uint32_t ih, uint32_t il) {
  const uint32_t d = hsub2(x, mean2);
  return hfma2(d, ih, hmul2(d, il));
}
__device__ __forceinline__ uint32_t modul(uint32_t n, uint32_t c1, uint32_t sh) { return hadd2(hmul2(n, c1), sh); }
__device__ __forceinline__ uint32_t ln_mod(uint32_t x, uint32_t mean2, uint32_t ih, uint32_t il, uint32_t c1, uint32_t sh) {
  return modul(ln_norm(x, mean2, ih, il), c1, sh);
}

#define R8(a, i) "+f"(a[i]), "+f"(a[i + 1]), "+f"(a[i + 2]), "+f"(a[i + 3]), "+f"(a[i + 4]), "+f"(a[i + 5]), "+f"(a[i + 6]), "+f"(a[i + 7])
#define D64 "{%0,%1,%2,%3,%4,%5,%6,%7,%8,%9,%10,%11,%12,%13,%14,%15,%16,%17,%18,%19,%20,%21,%22,%23,%24,%25,%26,%27,%28,%29,%30,%31," \
            "%32,%33,%34,%35,%36,%37,%38,%39,%40,%41,%42,%43,%44,%45,%46,%47,%48,%49,%50,%51,%52,%53,%54,%55,%56,%57,%58,%59,%60,%61,%62,%63}"
template <int TB>
__device__ __forceinline__ void mma_ss(float (&d)[64], uint64_t da, uint64_t db, int sc) {
  asm volatile("{\n.reg .pred p;\nsetp.ne.b32 p, %66, 0;\n"
               "wgmma.mma_async.sync.aligned.m64n128k16.f32.bf16.bf16 " D64 ", %64, %65, p, 1, 1, 0, %67;\n}"
               : R8(d, 0), R8(d, 8), R8(d, 16), R8(d, 24), R8(d, 32), R8(d, 40), R8(d, 48), R8(d, 56)
               : "l"(da), "l"(db), "r"(sc), "n"(TB));
}
template <int TB>
__device__ __forceinline__ void mma_rs(float (&d)[64], uint32_t a0, uint32_t a1, uint32_t a2, uint32_t a3, uint64_t db, int sc) {
  asm volatile("{\n.reg .pred p;\nsetp.ne.b32 p, %69, 0;\n"
               "wgmma.mma_async.sync.aligned.m64n128k16.f32.bf16.bf16 " D64 ", {%64,%65,%66,%67}, %68, p, 1, 1, %70;\n}"
               : R8(d, 0), R8(d, 8), R8(d, 16), R8(d, 24), R8(d, 32), R8(d, 40), R8(d, 48), R8(d, 56)
               : "r"(a0), "r"(a1), "r"(a2), "r"(a3), "l"(db), "r"(sc), "n"(TB));
}
#define D128 "{%0,%1,%2,%3,%4,%5,%6,%7,%8,%9,%10,%11,%12,%13,%14,%15,%16,%17,%18,%19,%20,%21,%22,%23,%24,%25,%26,%27,%28,%29,%30,%31," \
             "%32,%33,%34,%35,%36,%37,%38,%39,%40,%41,%42,%43,%44,%45,%46,%47,%48,%49,%50,%51,%52,%53,%54,%55,%56,%57,%58,%59,%60,%61,%62,%63," \
             "%64,%65,%66,%67,%68,%69,%70,%71,%72,%73,%74,%75,%76,%77,%78,%79,%80,%81,%82,%83,%84,%85,%86,%87,%88,%89,%90,%91,%92,%93,%94,%95," \
             "%96,%97,%98,%99,%100,%101,%102,%103,%104,%105,%106,%107,%108,%109,%110,%111,%112,%113,%114,%115,%116,%117,%118,%119,%120,%121,%122,%123,%124,%125,%126,%127}"
#define R128(d, e) R8(d, 0), R8(d, 8), R8(d, 16), R8(d, 24), R8(d, 32), R8(d, 40), R8(d, 48), R8(d, 56), \
                   R8(e, 0), R8(e, 8), R8(e, 16), R8(e, 24), R8(e, 32), R8(e, 40), R8(e, 48), R8(e, 56)
__device__ __forceinline__ void mma256_ss(float (&d)[64], float (&e)[64], uint64_t da, uint64_t db, int sc) {
  asm volatile("{\n.reg .pred p;\nsetp.ne.b32 p, %130, 0;\n"
               "wgmma.mma_async.sync.aligned.m64n256k16.f32.bf16.bf16 " D128 ", %128, %129, p, 1, 1, 0, 1;\n}"
               : R128(d, e) : "l"(da), "l"(db), "r"(sc));
}
__device__ __forceinline__ void mma256_rs(float (&d)[64], float (&e)[64], uint32_t a0, uint32_t a1, uint32_t a2, uint32_t a3, uint64_t db) {
  asm volatile("{\n.reg .pred p;\nsetp.ne.b32 p, 1, 0;\n"
               "wgmma.mma_async.sync.aligned.m64n256k16.f32.bf16.bf16 " D128 ", {%128,%129,%130,%131}, %132, p, 1, 1, 1;\n}"
               : R128(d, e) : "r"(a0), "r"(a1), "r"(a2), "r"(a3), "l"(db));
}
template <int N> __device__ __forceinline__ void keep(float (&a)[N]) {
#pragma unroll
  for (int i = 0; i < N; i++) asm volatile("" : "+f"(a[i])::"memory");
}
template <int N> __device__ __forceinline__ void keep(uint32_t (&a)[N]) {
#pragma unroll
  for (int i = 0; i < N; i++) asm volatile("" : "+r"(a[i])::"memory");
}

#define STAMP(idx) do {} while (0)
#define PROF(grp, cond, idx) do {} while (0)

constexpr float SCL2 = 1.4426950408889634f * 0.08838834764831845f;

__device__ __forceinline__ void pack_p(const float (&s)[64], uint32_t (&p)[32]) {
#pragma unroll
  for (int i = 0; i < 32; i++) p[i] = pack_bf(s[2 * i], s[2 * i + 1]);
}

__device__ __forceinline__ void issue_qk(float (&s)[64], uint32_t q0, uint32_t q1, uint32_t kslot) {
  const uint64_t db = make_desc(kslot, 16, 1024), da0 = make_desc(q0, 16, 1024), da1 = make_desc(q1, 16, 1024);
#pragma unroll
  for (int kk = 0; kk < 8; kk++) mma_ss<0>(s, (kk < 4 ? da0 : da1) + (kk & 3) * 2, db + (kk >> 2) * 1024 + (kk & 3) * 2, kk != 0);
}
__device__ __forceinline__ void issue_pv(float (&o)[64], uint32_t (&p)[32], uint32_t vslot, int acc) {
  uint64_t db = make_desc(vslot, 16384, 1024);
#pragma unroll
  for (int kk = 0; kk < 8; kk++)
    mma_rs<1>(o, p[4 * kk], p[4 * kk + 1], p[4 * kk + 2], p[4 * kk + 3], db + kk * 128, kk == 0 ? acc : 1);
}

template <int H>
__device__ __forceinline__ void store_chunk(const float (&a)[64], uint32_t addr) {
#pragma unroll
  for (int i = 8 * H; i < 8 * H + 8; i += 2)
    stmatrix4(addr ^ ((i & 7) << 4), pack_bf(a[4 * i], a[4 * i + 1]), pack_bf(a[4 * i + 2], a[4 * i + 3]),
              pack_bf(a[4 * i + 4], a[4 * i + 5]), pack_bf(a[4 * i + 6], a[4 * i + 7]));
}
template <int H>
__device__ __forceinline__ void store_chunk(const float (&a)[64], float i0, float i1, uint32_t addr) {
#pragma unroll
  for (int i = 8 * H; i < 8 * H + 8; i += 2)
    stmatrix4(addr ^ ((i & 7) << 4), pack_bf(a[4 * i] * i0, a[4 * i + 1] * i0), pack_bf(a[4 * i + 2] * i1, a[4 * i + 3] * i1),
              pack_bf(a[4 * i + 4] * i0, a[4 * i + 5] * i0), pack_bf(a[4 * i + 6] * i1, a[4 * i + 7] * i1));
}
__device__ __forceinline__ float inv_quad_sum(float l) {
  l += __shfl_xor_sync(0xffffffffu, l, 1);
  l += __shfl_xor_sync(0xffffffffu, l, 2);
  return rcp(l);
}

__device__ __forceinline__ void ln_scalars(float mean, float var, float& mb, float& sd) {
  mb = rbf(mean);
  float r; asm("sqrt.approx.ftz.f32 %0, %1;" : "=f"(r) : "f"(rbf(rbf(var) + 1e-5f)));
  sd = rbf(r);
}

__global__ void __cluster_dims__(2, 1, 1) __launch_bounds__(384, 1) fused_kernel(const __grid_constant__ Maps maps, const Ptrs P) {
  extern __shared__ __align__(1024) uint8_t smem_raw[];
  const uint32_t base = smem_u32(smem_raw);
  const int tid = threadIdx.x, lane = tid & 31;
  const int warp = __shfl_sync(0xffffffffu, tid >> 5, 0);
  const int b = blockIdx.x;
  PROF(31, tid == 0, 0);

  if (b >= NMAIN) {
    float* sc = reinterpret_cast<float*>(smem_raw);
    float* red = sc + DM;
    for (int k = tid; k < DM; k += 384) sc[k] = rbf(silu_f(__bfloat162float(P.c[k])));
    __syncthreads();
    if (tid < 256) {
      const int col = 2048 + (b - NMAIN) * 1024 + (tid & 127) * 8, r0 = (tid >> 7) * 512;
      float acc[8];
#pragma unroll
      for (int e = 0; e < 8; e++) acc[e] = 0.f;
#pragma unroll 1
      for (int r = r0; r < r0 + 512; r += HU) {
        uint4 w[HU];
#pragma unroll
        for (int u = 0; u < HU; u++) w[u] = ldg_stream4(P.w_mod + (size_t)(r + u) * NMOD + col);
#pragma unroll
        for (int u = 0; u < HU; u++) {
          float s = sc[r + u];
          acc[0] += s * bf_lo(w[u].x); acc[1] += s * bf_hi(w[u].x); acc[2] += s * bf_lo(w[u].y); acc[3] += s * bf_hi(w[u].y);
          acc[4] += s * bf_lo(w[u].z); acc[5] += s * bf_hi(w[u].z); acc[6] += s * bf_lo(w[u].w); acc[7] += s * bf_hi(w[u].w);
        }
      }
      if (tid >= 128) {
#pragma unroll
        for (int e = 0; e < 8; e++) red[(tid & 127) * 8 + e] = acc[e];
      }
      const uint32_t tag = ld_relaxed(&g_epoch) % 3 + 1;
      bar_sync(1, 256);
      if (tid < 128) {
        uint32_t o[8];
#pragma unroll
        for (int e = 0; e < 8; e++) o[e] = __float_as_uint(rbf(acc[e] + red[tid * 8 + e])) | tag;
        st_relaxed4(g_mod + col, o[0], o[1], o[2], o[3]);
        st_relaxed4(g_mod + col + 4, o[4], o[5], o[6], o[7]);
        const uint4 wr = ldg_nc4(P.w_r + tid * 8);
        const uint32_t wv[4] = {wr.x, wr.y, wr.z, wr.w};
        float dsum = 0.f;
#pragma unroll
        for (int e = 0; e < 8; e++) {
          const float m = bf_hi(o[e]);
          dsum += (b == NMAIN + 2 ? rbf(1.f + m) : m) * ((e & 1) ? bf_hi(wv[e >> 1]) : bf_lo(wv[e >> 1]));
        }
#pragma unroll
        for (int k = 16; k > 0; k >>= 1) dsum += __shfl_xor_sync(0xffffffffu, dsum, k);
        if (lane == 0) st_relaxed(g_mod + (b - NMAIN) * 4 + warp, tagf(dsum, tag));
      }
    }
    PROF(2, tid == 0, 1);
    return;
  }

  const int rank = b & 1;
  const int rb = ((b >> 4) << 1) | rank, cj = (b >> 1) & 7;
  const uint32_t bfull = base + OFF_BAR, bempty = bfull + NSLOT * 8;
  const uint32_t gfull = bempty + NSLOT * 8, gempty = gfull + 32;
  const uint32_t bar_ofull = gempty + 32;
  const uint32_t bar_ofree = bar_ofull + 32;
  const uint32_t bar_par = bar_ofree + 32;
  const uint32_t bar_mod = bar_par + 8;
  const uint32_t bar_pread = bar_mod + 8;
  const uint32_t bar_xres = bar_pread + 8;
  const uint32_t bar_ring = bar_xres + 8;
  const uint32_t bar_box = bar_ring + 24;
  const uint32_t bar_go = bar_box + 96;
  const uint32_t bar_go2 = bar_go + 16;
  const uint32_t bar_cnt = bar_go + 24;
  const uint32_t xfull = bar_go + 32, xempty = xfull + 32;
  const uint32_t bar_hw = xempty + 32, bar_hx = bar_hw + 8;
  const uint32_t bar_hpub = bar_hx + 16;
  const uint32_t bar_win = bar_hpub + 8;
  const uint32_t bar_rx = bar_win + 8;
  const uint32_t bar_sel = bar_rx + 8;
  const uint32_t bar_gate = bar_sel + 8;
  const uint32_t bar_rel = bar_gate + 8;
  const uint32_t bar_od = bar_rel + 8;
  const uint32_t bar_res = bar_go + 8;
  const uint32_t stage = base + OFF_STAGE, par = base + OFF_PAR;

  if (warp == 8 && elect_one()) {
    for (int s = 0; s < NSLOT; s++) { mbar_init(bfull + s * 8, 1); mbar_init(bempty + s * 8, 16); }
    for (int s = 0; s < 4; s++) { mbar_init(gfull + s * 8, 1); mbar_init(gempty + s * 8, 16); mbar_init(xfull + s * 8, 1); mbar_init(xempty + s * 8, 8); mbar_init(bar_ofree + s * 8, 1); mbar_init(bar_ofull + s * 8, 128); }
    mbar_init(bar_par, 64); mbar_init(bar_mod, 256); mbar_init(bar_pread, 2); mbar_init(bar_xres, 1);
    mbar_init(bar_ring, 8); mbar_init(bar_ring + 8, 8); mbar_init(bar_ring + 16, 8);
    mbar_init(bar_go, 1); mbar_init(bar_go2, 1); mbar_init(bar_cnt, 1); mbar_init(bar_hpub, 8); mbar_init(bar_res, 1); mbar_init(bar_win, 1); mbar_init(bar_rx, 1); mbar_init(bar_sel, 64); mbar_init(bar_gate, 8); mbar_init(bar_rel, 8); mbar_init(bar_od, 1);
    for (int s = 0; s < 12; s++) mbar_init(bar_box + s * 8, 1);
    asm volatile("fence.mbarrier_init.release.cluster;" ::: "memory");
    prefetch_map(&maps.x); prefetch_map(&maps.wq); prefetch_map(&maps.k); prefetch_map(&maps.v);
  }
  if (warp == 9 && elect_one()) {
    mbar_init(bar_hw, 1); mbar_init(bar_hx, 1); mbar_init(bar_hx + 8, 1);
    asm volatile("fence.mbarrier_init.release.cluster;" ::: "memory");
    mbar_expect_tx(bar_hw, 32768);
    mbar_expect_tx(bar_hx, 16384);
    mbar_expect_tx(bar_hx + 8, 16384);
    const __nv_bfloat16* xs = P.x + (size_t)(rb * 128 + cj * 16) * DM;
    bulk_load(base + 2 * GST_BYTES, xs, 16384, bar_hx);
    tma2d(stage, &maps.wm, (b >> 1) * 32, rank * 512, bar_hw);
    tma2d(stage + 16384, &maps.wm, (b >> 1) * 32, rank * 512 + 256, bar_hw);
    bulk_load(base + 3 * GST_BYTES, xs + 8 * DM, 16384, bar_hx + 8);
  }
  cluster_arrive();

  if (warp >= 8) {
    asm volatile("setmaxnreg.dec.sync.aligned.u32 40;");
    if (warp < 10) bar_arrive(1, 320);
    const uint32_t epoch = ld_relaxed(&g_epoch);
    cluster_wait();
    if (warp == 8) {
      const int kvrow = (cj >> 1) * SK + (SK - WIN);
      int wch = cj * 8 + rank * 2;
#pragma unroll 1
      for (int ps = 0; ps < 3; ps++) {
        const CUtensorMap* mw = ps == 2 ? &maps.wo : &maps.wq;
        const uint32_t xt = ps == 1 ? XT1 : XT2, wt = ps == 0 ? WT0 : (ps == 1 ? WT1 : WT2);
        const int nst = ps == 2 ? 32 : 16;
#pragma unroll 1
        for (int i = 0; i < nst; i++) {
          const uint32_t bf = gfull + (i & 3) * 8;
          const int kt = ps == 2 ? (((cj & 1) * 4 + ((i >> 1) & 3)) * 4 + (i >> 3)) * 2 + (i & 1) : (i + (ps ? 0 : b & 14)) & 15;
          const uint32_t wd = base + unit_of(wt, i & 3) + rank * UNIT, xd = base + unit_of(xt, i & 3);
          const uint8_t* xs = g_act + (uint32_t)(rb * 80 + (ps - 1) * 16 + kt) * UNIT;
          if (ps == 0 && i == HD) mbar_wait(bar_mod, 0);
          const bool xfirst = ps && i < 2;
          if (ps == 2 && i == 0) mbar_wait(bar_ofree + 24, 0);
          if (i == 0) fence_async();
          mbar_wait(gempty + (i & 3) * 8, ((i >> 2) & 1) ^ 1);
          if (elect_one()) {
            mbar_expect_tx(bf, ps ? GST_BYTES : 2 * UNIT);
            if (xfirst) bulk_load_stream(xd, xs, UNIT, bf);
          }
          if (ps && i < 4) mbar_wait(bempty + i * 8, 1);
          if (elect_one()) tma3d_mc<true>(wd, mw, 0, (i == 31 ? kt ^ (rank * 32) : kt) * 64, i == 31 ? cj * 2 : wch, bf);
          if (ps) {
            if (i == 16) { mbar_wait(bar_cnt, 0); fence_async(); }
            if (i == 2) mbar_wait(bar_ofree + (ps - 1) * 16, 0);
            if (elect_one()) {
              if (i == 31) bulk_load(xd, xs, UNIT, bf); else if (!xfirst) bulk_load_stream(xd, xs, UNIT, bf);
              mbar_arrive_pred(bar_go, i == GOST - 1);
              mbar_arrive_pred(bar_od, i == ODS);
              mbar_arrive_pred(bar_res, ((1u << RES0 | 1u << RES1) >> i) & 1);
            }
          }
        }
        if (ps == 2) break;
        wch = ps ? ((wch >> 3) ^ rank) * 2 : wch + 4;
#pragma unroll 1
        for (int u = 0; u < 16; u++) {
          const bool isk = (u == 0) || ((u & 1) && u < 15);
          const int blk = (isk ? (u + 1) >> 1 : (u == 15 ? 7 : (u >> 1) - 1)) & 3;
          const uint32_t sl = base + unit_of(ps ? AT1 : AT0, u & 3) + rank * UNIT, bf = bfull + (u & 3) * 8;
          if (u < 4) mbar_wait(gempty + ((u + 1) >> 1) * 8, 1);
          mbar_wait(bempty + (u & 3) * 8, ((u >> 2) & 1) ^ 1);
          if (elect_one()) {
            mbar_arrive_pred(bar_go2, ps && u == PG0);
            mbar_expect_tx(bf, SLOT_BYTES);
            tma3d_mc<false>(sl, isk ? &maps.k : &maps.v, 0, kvrow + blk * 128, rank, bf);
          }
        }
      }
      if (elect_one()) mbar_expect_tx(bar_rx, UNIT);
      mbar_wait(bar_rel, 0);
      if (elect_one()) {
        bulk_load_stream(base + UNIT, g_act + (uint32_t)(rb * 80 + 16 + 63 - (cj & 1) * 32) * UNIT, UNIT, bar_rx);
      }
      if (b < NFFN) {
#pragma unroll 1
        for (int u = 0; u < 12; u++) {
          const uint32_t dst = base + unit_of(u < 4 ? FT_G : (u < 8 ? FT_U : FT_D), u & 3);
          if (elect_one()) mbar_expect_tx(bar_box + u * 8, UNIT);
          if (u == FB0 || u == 2 || u == FB2) mbar_wait(bar_ring + (u == FB2 ? 16 : (u + 6) & 8), 0);
          if (u >= FPACE) mbar_wait(bar_box + (u - FPACE) * 8, 0);
          if (elect_one()) {
            if (u < 8) tma2d(dst, u < 4 ? &maps.wg : &maps.wu, b * 32, (u & 3) * 256, bar_box + u * 8);
            else tma3d(dst, &maps.wd, 0, b * 32, (u - 8) * 4, bar_box + u * 8);
          }
        }
      }
    } else if (warp == 9) {
      const uint32_t target = 8 * (epoch + 1);
#pragma unroll 1
      for (int i = 0; i < 16; i++) {
        if (i == HDX) mbar_wait(bar_mod, 0);
        if (i == NRS) {
          wait_counter(&g_cnt_h[rb * 32], 2 * target);
          PROF(1, lane == 0, 26);
          fence_async();
        }
        mbar_wait(xempty + (i & 3) * 8, ((i >> 2) & 1) ^ 1);
        if (elect_one()) {
          mbar_expect_tx(xfull + (i & 3) * 8, UNIT);
          if (i < NRS) tma2d(base + (i & 3) * GST_BYTES, &maps.x, ((2 * cj + i) & 15) * 64, rb * 128, xfull + (i & 3) * 8);
          else bulk_load_stream(base + (i & 3) * GST_BYTES, g_act + (uint32_t)(rb * 80 + ((2 * cj + i) & 15)) * UNIT, UNIT, xfull + (i & 3) * 8);
        }
      }
      prefetch_map(&maps.wo);
#pragma unroll 1
      for (int t = 0; t < 4; t++) {
        if (t & 1) mbar_wait(bar_od, t >> 1);
#pragma unroll 1
        for (int p = 0; p < 32768 / OPS; p++) {
          const uint32_t w = p / (16384 / OPS), c = (p / (8192 / OPS)) & 1, off = w * 8192 + (p % (8192 / OPS)) * OPS;
          mbar_wait(bar_ofull + (t & 1) * 16 + w * 8, t >> 1);
          if (elect_one()) {
            bulk_store(g_act + (uint32_t)(rb * 80 + 16 + (cj * 4 + t) * 2 + c) * UNIT + off, base + unit_of(QT, 2 * t + c) + off, OPS);
            asm volatile("cp.async.bulk.commit_group;" ::: "memory");
            asm volatile("cp.async.bulk.wait_group.read %0;" ::"n"(OFL) : "memory");
          }
        }
        if (elect_one()) {
          asm volatile("cp.async.bulk.wait_group.read 0;" ::: "memory");
          mbar_arrive_pred(bar_ofree + t * 8, t < 3);
          asm volatile("cp.async.bulk.wait_group 0;" ::: "memory");
          fence_async();
          red_release(&g_cnt_o[((rb * 4 + t) * 2 + (cj >> 2)) * 32], 2);
        }
        if (t & 1) {
          wait_counter(&g_cnt_o[(rb * 8 + 2 * t - 2 + (cj & 1)) * 32], target);
          wait_counter(&g_cnt_o[(rb * 8 + 2 * t + (cj & 1)) * 32], target);
          if (elect_one()) mbar_arrive_pred(bar_ofree + 24, t == 1);
        }
      }
      wait_counter(&g_cnt_o[(rb * 8 + 7 - (cj & 1)) * 32], target);
      fence_async();
      if (elect_one()) {
        mbar_arrive(bar_cnt);
        PROF(2, true, 27);
        mbar_expect_tx(bar_xres, 32768);
      }
#pragma unroll 1
      for (int u = 0; u < 2; u++) {
        mbar_wait(bar_res, u);
        if (elect_one()) tma2d(base + OFF_RES + u * UNIT, &maps.x, cj * 128 + u * 64, rb * 128, bar_xres);
      }
      const uint32_t tag = epoch % 3 + 1;
      const uint32_t* inbox = g_cand + (lane & 15);
      mbar_wait(bar_ring + 16, 0);
      uint32_t c0 = ld_relaxed(inbox), n = 0;
#define CAND_STEP(cv)                                                                                        \
      {                                                                                                      \
        const bool valid = (cv & 3u) == tag, all = __all_sync(0xffffffffu, valid);                           \
        const uint32_t best = __reduce_max_sync(0xffffffffu, valid ? cv : 0u);                               \
        const uint32_t blk = __ffs(__ballot_sync(0xffffffffu, cv == best)) - 1;                              \
        if (best) sts2(par + PAR_CONST + 56, best, (blk << 7 | (~best >> 2 & 127)) | (all ? 0x1800 : 0x800)); \
        if (all) break;                                                                                      \
        cv = ld_relaxed(inbox);                                                                              \
      }
      while (true) { CAND_STEP(c0) watchdog(n); }
    } else {
      const int t2 = tid - 320;
      mbar_wait(bar_hpub, 0);
      PROF(1, t2 == 0, 24);
#pragma unroll 1
      for (int c = 0; c < 8; c++) {
        const uint32_t off = (warp & 1) * UNIT + c * 2048 + lane * 16;
        uint8_t* dst = g_act + (uint32_t)(rb * 80 + cj * 2) * UNIT + off;
        const uint4 v0 = lds4(stage + off), v1 = lds4(stage + off + 512), v2 = lds4(stage + off + 1024), v3 = lds4(stage + off + 1536);
        stg4(dst, v0); stg4(dst + 512, v1); stg4(dst + 1024, v2); stg4(dst + 1536, v3);
      }
      __syncwarp();
      if (lane == 0) {
        mbar_arrive(bar_pread);
        red_release(&g_cnt_h[rb * 32], 1);
        PROF(1, t2 == 0, 25);
        prefetch_map(&maps.wg); prefetch_map(&maps.wu); prefetch_map(&maps.wd); prefetch_map(&maps.out);
      }
      __syncwarp();
      if (b < NFFN) {
        mbar_wait(bar_go2, 0);
        const __nv_bfloat16* pg = ((b & 1) ? P.w_up : P.w_gate) + (b >> 1) * 64 + (size_t)t2 * FF;
        const __nv_bfloat16* pd = P.w_down + (size_t)b * 32768 + t2 * 64;
        PROF(2, t2 == 0, 13);
#pragma unroll 1
        for (int i = 0; i < WN; i += WB) {
          uint32_t v[WB];
#pragma unroll
          for (int u = 0; u < WB; u++) {
            const int k = i + u;
            asm volatile("ld.global.cg.L2::128B.u32 %0, [%1];" : "=r"(v[u]) : "l"(k < 16 ? pg + (size_t)k * 64 * FF : pd + (k - 16) * 4096));
          }
#pragma unroll
          for (int u = 1; u < WB; u++) v[0] ^= v[u];
          sts1(par + PAR_SINK + t2 * 4, v[0]);
        }
        PROF(2, t2 == 0, 14);
      }
      const uint32_t tag = epoch % 3 + 1;
      mbar_wait(bar_go, 0);
      if (warp == 10) {
        const uint32_t* src = g_mod + 2 * DM + cj * 128 + lane * 4;
        const uint2 wr = *reinterpret_cast<const uint2*>(P.w_r + cj * 128 + lane * 4);
        uint4 vga, vsb, vcb, vgb;
        uint32_t n = 0;
        do {
          vga = ld_relaxed4(src); vsb = ld_relaxed4(src + DM); vcb = ld_relaxed4(src + 2 * DM); vgb = ld_relaxed4(src + 3 * DM);
          watchdog(n);
        } while (!__all_sync(0xffffffffu, tag_ok(vga, tag) && tag_ok(vsb, tag) && tag_ok(vcb, tag) && tag_ok(vgb, tag)));
        const float c0 = rbf(1.f + bf_hi(vcb.x)), c1 = rbf(1.f + bf_hi(vcb.y)), c2 = rbf(1.f + bf_hi(vcb.z)), c3 = rbf(1.f + bf_hi(vcb.w));
        const float a0 = c0 * bf_lo(wr.x), a1 = c1 * bf_hi(wr.x), a2 = c2 * bf_lo(wr.y), a3 = c3 * bf_hi(wr.y);
        const uint32_t h0 = pack_bf(a0, a1), h1 = pack_bf(a2, a3);
        const uint32_t t1 = par + PAR_T1 + (lane >> 2) * 64 + (lane & 1) * 32 + (lane & 2) * 2;
        sts1(t1, h0); sts1(t1 + 8, pack_bf(a0 - bf_lo(h0), a1 - bf_hi(h0)));
        sts1(t1 + 16, h1); sts1(t1 + 24, pack_bf(a2 - bf_lo(h1), a3 - bf_hi(h1)));
        sts4(par + PAR_T2 + lane * 32, make_uint4(pack_bf(c0, c1), __byte_perm(vsb.x, vsb.y, 0x7632), __byte_perm(vgb.x, vgb.y, 0x7632), __byte_perm(vga.x, vga.y, 0x7632)));
        sts4(par + PAR_T2 + lane * 32 + 16, make_uint4(pack_bf(c2, c3), __byte_perm(vsb.z, vsb.w, 0x7632), __byte_perm(vgb.z, vgb.w, 0x7632), __byte_perm(vga.z, vga.w, 0x7632)));
      } else {
        const uint4 g = poll4((lane & 2) ? g_mod + 8 - (lane & 1) * 4 : g_mod + 5 * DM + b * 8 + (lane & 1) * 4, tag);
        sts1(par + PAR_CONST + 60, 0);
        if (lane < 2) sts4(par + PAR_CONST + 16 + lane * 16, g);
        else if (lane < 4) sts2(par + PAR_CONST + (lane - 2) * 8, __float_as_uint(untag_sum(g.x, g.y) + untag_sum(g.z, g.w)), epoch);
      }
      __syncwarp();
#pragma unroll 4
      for (int q = XR; q < XE; q++) st_b128(g_xch + ((size_t)b * 8 * 256 + q * 64 + t2) * 4, (epoch & 1) << 16, 0, 0, 0);
      for (int q = 0; q < 2; q++) st_relaxed4(g_stats + ((size_t)cj * SEQ + rb * 128 + q * 64 + t2) * 4, 0, 0, 0, 0);
      if (b < NFFN)
        for (int q = 0; q < 4; q++) st_relaxed4(g_ypart + ((size_t)(q * 32 + (t2 >> 1)) * NFFN + b) * 8 + (t2 & 1) * 4, 0, 0, 0, 0);
      st_relaxed4(g_row + rb * 2 * DM + (t2 >> 5) * DM + cj * 128 + (t2 & 31) * 4, 0, 0, 0, 0);
      __threadfence();
      mbar_arrive(bar_par);
      mbar_wait(bar_gate, 0);
      uint32_t have = 0, n = 0;
      while (true) {
        const uint32_t st = lds1(par + PAR_CONST + 60) >> 7;
        if ((st & 31) != have) {
          const uint32_t* hsrc = g_row + (st & 15) * 2 * DM + t2 * 4;
          uint4 hv[4];
          bool ok = true;
#pragma unroll
          for (int i = 0; i < 4; i++) hv[i] = ld_pairs(hsrc + i * 256);
#pragma unroll
          for (int i = 0; i < 4; i++) {
            sts2(base + ((FT_G >> i * 4) & 15) * UNIT + (warp & 1) * 8192 + 256 + lane * 8, hv[i].x, hv[i].z);
            ok = ok && hv[i].y == tag && hv[i].w == tag;
          }
          have = __all_sync(0xffffffffu, ok) ? st & 31 : 0;
        }
        if ((st ^ have) == 32) break;
        watchdog(n);
      }
      mbar_arrive(bar_sel);
    }
    __syncwarp();
    cluster_arrive();
    {
      const uint32_t tag = epoch % 3 + 1, t3 = tid - 256;
      mbar_wait(bar_win, 0);
      uint2 win = lds2(par + PAR_CONST + 56);
      win.y &= 0x7ff;
      const uint32_t* fsrc = g_row + (win.y >> 7) * 2 * DM + (b >> 1) * 16 + (t3 & 3) * 4 + (b & 1) * 2;
      const uint32_t* ysrc = g_ypart + (size_t)b * NFFN * 8 + min(t3, NFFN - 1) * 4;
      uint2 fh = ld_pair(fsrc), fx = ld_pair(fsrc + DM);
      if (PSL) __nanosleep(PSL);
      uint4 ya = ld_relaxed4(ysrc), yb = ld_relaxed4(ysrc + NFFN * 4);
      const float rwin = __uint_as_float(((int)win.x < 0 ? win.x & 0x7fffffffu : ~win.x) & ~0x1ffu);
      const float rs = rbf(rcp(1.f + __expf(-rbf(rwin))));
      uint32_t n = 0;
      while (__any_sync(0xffffffffu, fh.y != tag || fx.y != tag)) { fh = ld_pair(fsrc); fx = ld_pair(fsrc + DM); watchdog(n); }
      while (!__all_sync(0xffffffffu, tag_ok(ya, tag) && tag_ok(yb, tag))) {
        if (!tag_ok(ya, tag)) ya = ld_relaxed4(ysrc);
        if (!tag_ok(yb, tag)) yb = ld_relaxed4(ysrc + NFFN * 4);
        watchdog(n);
      }
      __syncwarp();
      PROF(8, t3 == 0, 5);
      float y0 = untag_sum(ya.x, yb.x), y1 = untag_sum(ya.y, yb.y), y2 = untag_sum(ya.z, yb.z), y3 = untag_sum(ya.w, yb.w);
      const bool u1 = lane & 2, u2 = lane & 4;
      y0 = (u1 ? y2 : y0) + __shfl_xor_sync(0xffffffffu, u1 ? y0 : y2, 2);
      y1 = (u1 ? y3 : y1) + __shfl_xor_sync(0xffffffffu, u1 ? y1 : y3, 2);
      y0 = (u2 ? y1 : y0) + __shfl_xor_sync(0xffffffffu, u2 ? y0 : y1, 4);
      y0 += __shfl_xor_sync(0xffffffffu, y0, 8);
      if (!(lane & 8)) sts1(par + PAR_RED + 64 + (t3 >> 4) * 32 + ((lane & 1) * 4 + (lane & 2) + ((lane >> 2) & 1)) * 4, __float_as_uint(y0));
      bar_sync(4, 128);
      if (t3 < 4) {
        y0 = 0.f; y1 = 0.f;
#pragma unroll
        for (int w4 = 0; w4 < 7; w4++) {
          const uint2 v = lds2(par + PAR_RED + 64 + w4 * 32 + t3 * 8);
          y0 += __uint_as_float(v.x); y1 += __uint_as_float(v.y);
        }
        const uint2 gv = lds2(par + PAR_CONST + 16 + t3 * 8);
        const uint32_t upd = hmul2(pack_bf(y0, y1), pack_bf(rs, rs));
        *reinterpret_cast<uint32_t*>(P.out + (size_t)win.y * DM + b * 8 + t3 * 2) =
            hadd2(fx.x, hmul2(__byte_perm(gv.x, gv.y, 0x7632), hadd2(fh.x, upd)));
        if (b == 0 && t3 == 0) st_relaxed(&g_epoch, epoch + 1);
      }
      PROF(31, t3 == 0, 36);
    }
    cluster_wait();
  } else {
    const int wg = warp >> 2;

    uint32_t tag;
    {
      uint32_t* const pmod = g_modp + rank * 2 * DM + (b >> 1) * 32 + lane;
      uint32_t* const pln = g_ln1 + (rb * 128 + cj * 16 + warp) * 4;
      const uint32_t cv = ldg_nc1(P.c + rank * 512 + tid * 2);
      const uint32_t epoch = ld_relaxed(&g_epoch);
      if (warp == 0) st_relaxed(pmod, 0);
      if (lane == 0) { st_b128(pln, 0, 0, 0, 0); st_b128(pln + 32, 0, 0, 0, 0); }
      asm volatile("setmaxnreg.inc.sync.aligned.u32 232;");
      sts1(par + tid * 4, pack_bf(silu_f(bf_lo(cv)), silu_f(bf_hi(cv))));
      bar_sync(1, 320);
      tag = epoch % 3 + 1;
#pragma unroll
      for (int part = 0; part < 3; part++) {
        if (part != 1) {
          const uint32_t xa = base + (2 + part / 2) * GST_BYTES + warp * 2048 + lane * 16;
          mbar_wait(bar_hx + part * 4, 0);
          float s0 = 0.f, s1 = 0.f, q0 = 0.f, q1 = 0.f;
#pragma unroll
          for (int q = 0; q < 4; q++) {
            const uint4 xv = lds4(xa + q * 512);
            const uint32_t u[4] = {xv.x, xv.y, xv.z, xv.w};
#pragma unroll
            for (int e = 0; e < 4; e++) { const float lo = bf_lo(u[e]), hi = bf_hi(u[e]); s0 += lo; s1 += hi; q0 += lo * lo; q1 += hi * hi; }
          }
          s0 += s1; q0 += q1;
#pragma unroll
          for (int o = 16; o > 0; o >>= 1) { s0 += __shfl_xor_sync(0xffffffffu, s0, o); q0 += __shfl_xor_sync(0xffffffffu, q0, o); }
          const float mean = s0 * (1.f / DM);
          float mb, sd;
          ln_scalars(mean, fmaxf(q0 * (1.f / DM) - mean * mean, 0.f), mb, sd);
          uint32_t ih, il;
          split_inv(sd, ih, il);
          if (lane == 0) st_b128(pln + part * 16, pack_bf(mb, mb), ih, il, tag);
          PROF(1, tid == 0 && part == 2, 4);
        } else {
          float acc[8];
#pragma unroll
          for (int e = 0; e < 8; e++) acc[e] = 0.f;
          const uint32_t wa = stage + (tid >> 2) * 64 + (((tid ^ (tid >> 3)) & 3) << 4), sa = par + (tid >> 3) * 4, sh = (tid & 4) ? 0x3244 : 0x1044;
          mbar_wait(bar_hw, 0);
#pragma unroll
          for (int p = 0; p < 8; p++) {
            const uint4 w = lds4(wa + p * 4096);
            const float s = __uint_as_float(__byte_perm(lds1(sa + p * 128), 0, sh));
            acc[0] += s * bf_lo(w.x); acc[1] += s * bf_hi(w.x); acc[2] += s * bf_lo(w.y); acc[3] += s * bf_hi(w.y);
            acc[4] += s * bf_lo(w.z); acc[5] += s * bf_hi(w.z); acc[6] += s * bf_lo(w.w); acc[7] += s * bf_hi(w.w);
          }
#pragma unroll
          for (int e = 0; e < 4; e++) {
            const bool up = lane & 16;
            acc[e] = (up ? acc[e + 4] : acc[e]) + __shfl_xor_sync(0xffffffffu, up ? acc[e] : acc[e + 4], 16);
          }
#pragma unroll
          for (int e = 0; e < 2; e++) {
            const bool up = lane & 8;
            acc[e] = (up ? acc[e + 2] : acc[e]) + __shfl_xor_sync(0xffffffffu, up ? acc[e] : acc[e + 2], 8);
          }
          {
            const bool up = lane & 4;
            acc[0] = (up ? acc[1] : acc[0]) + __shfl_xor_sync(0xffffffffu, up ? acc[0] : acc[1], 4);
          }
          sts1(base + 2 * GST_BYTES + warp * 2048 + ((lane & 3) * 8 + (lane >> 2)) * 4, __float_as_uint(acc[0]));
          bar_sync(1, 256);
          if (warp == 0) {
            float s = 0.f;
#pragma unroll
            for (int w8 = 0; w8 < 8; w8++) s += __uint_as_float(lds1(base + 2 * GST_BYTES + w8 * 2048 + lane * 4));
            st_relaxed(pmod, (__float_as_uint(s) & ~3u) | tag);
          }
          PROF(1, tid == 0, 3);
        }
      }
      cluster_wait();
      if (wg == 1) bar_arrive(2, 256);
    }

    float f0 = 0.f, f1 = 0.f;
    const uint32_t rempty = lane < 2 ? mapa(bempty, lane & 1) : 0;
    constexpr uint32_t GE = NSLOT * 8 + 32;
    float o[64], s[64];
#pragma unroll 1
    for (int ps = 0; ps < 3; ps++) {
      {
        const uint32_t xt = ps == 1 ? XT1 : XT2, wt = ps == 1 ? WT1 : WT2;
        const int nst = ps == 2 ? 28 : 14;
        if (ps == 0) {
          float ga[64], gb[64];
#pragma unroll
          for (int i = 0; i < 64; i++) { ga[i] = 0.f; gb[i] = 0.f; }
          uint32_t a[2][16];
          const uint32_t l = fresh_lane();
          uint32_t fa[4];
#pragma unroll
          for (int kk = 0; kk < 4; kk++) fa[kk] = (base + wg * 8192 + frag_offset(warp)) ^ (kk * 32);
          const uint32_t mt = par + (l & 3) * 16;
          auto fetch = [&](int i, uint32_t (&f)[16]) {
            mbar_wait(xfull + (i & 3) * 8, i >> 2);
#pragma unroll
            for (int kk = 0; kk < 4; kk++) ldmatrix4(fa[kk] + (i & 3) * GST_BYTES, f[4 * kk], f[4 * kk + 1], f[4 * kk + 2], f[4 * kk + 3]);
          };
          uint4 r0, r1;
          {
            const uint32_t t7 = (warp & 3) * 32 + l;
            const uint32_t* pm = g_modp + wg * DM + ((cj * 128 + t7 * 4) & (DM - 1));
            const uint32_t* pr = g_ln1 + (rb * 128 + warp * 16 + (l >> 2)) * 4;
            uint4 m0 = ld_relaxed4(pm), m1 = ld_relaxed4(pm + 2 * DM);
            r0 = ld_b128(pr); r1 = ld_b128(pr + 32);
            fetch(0, a[0]); fetch(1, a[1]);
            uint32_t n = 0;
            bool written = false;
#pragma unroll 1
            while (true) {
              uint32_t miss;
              asm volatile("{ .reg .pred p0, p1, p2, p3; .reg .b32 t, u;\n"
                           "lop3.b32 t, %1, %2, %19, 0x7e; lop3.b32 u, %3, %4, %19, 0x7e; or.b32 t, t, u; and.b32 t, t, 3; setp.ne.u32 p0, t, 0;\n"
                           "lop3.b32 t, %5, %6, %19, 0x7e; lop3.b32 u, %7, %8, %19, 0x7e; or.b32 t, t, u; and.b32 t, t, 3; setp.ne.u32 p1, t, 0;\n"
                           "setp.ne.u32 p2, %12, %19; setp.ne.u32 p3, %16, %19;\n"
                           "@p0 ld.relaxed.gpu.global.v4.u32 {%1, %2, %3, %4}, [%17];\n"
                           "@p1 ld.relaxed.gpu.global.v4.u32 {%5, %6, %7, %8}, [%17 + 8192];\n"
                           "@p2 ld.relaxed.gpu.global.v4.u32 {%9, %10, %11, %12}, [%18];\n"
                           "@p3 ld.relaxed.gpu.global.v4.u32 {%13, %14, %15, %16}, [%18 + 128];\n"
                           "or.pred p0, p0, p1; or.pred p2, p2, p3; vote.sync.any.pred p0, p0, 0xffffffff; vote.sync.any.pred p2, p2, 0xffffffff;\n"
                           "selp.u32 t, 1, 0, p0; selp.u32 u, 2, 0, p2; or.b32 %0, t, u; }"
                           : "=r"(miss), "+r"(m0.x), "+r"(m0.y), "+r"(m0.z), "+r"(m0.w), "+r"(m1.x), "+r"(m1.y), "+r"(m1.z), "+r"(m1.w),
                             "+r"(r0.x), "+r"(r0.y), "+r"(r0.z), "+r"(r0.w), "+r"(r1.x), "+r"(r1.y), "+r"(r1.z), "+r"(r1.w)
                           : "l"(pm), "l"(pr), "r"(tag) : "memory");
              if (!(miss & 1) && !written) {
                written = true;
                float c0 = untag_sum(m0.x, m1.x), c1 = untag_sum(m0.y, m1.y), c2 = untag_sum(m0.z, m1.z), c3 = untag_sum(m0.w, m1.w);
                if (wg) { c0 = 1.f + rbf(c0); c1 = 1.f + rbf(c1); c2 = 1.f + rbf(c2); c3 = 1.f + rbf(c3); }
                const uint32_t d = par + (t7 >> 2) * 64 + (t7 & 1) * 32 + (t7 & 2) * 2 + (wg ? 0 : 8);
                sts1(d, pack_bf(c0, c1));
                sts1(d + 16, pack_bf(c2, c3));
                mbar_arrive(bar_mod);
              }
              if (!miss) break;
              watchdog(n);
            }
          }
          const uint32_t zero = r0.w ^ tag;
          auto normalize = [&](uint32_t (&f)[16]) {
#pragma unroll
            for (int k = 0; k < 16; k += 2) { f[k] = ln_norm(f[k], r0.x, r0.y, r0.z); f[k + 1] = ln_norm(f[k + 1], r1.x, r1.y, r1.z); }
          };
          auto modulate = [&](int i, uint32_t (&f)[16]) {
#pragma unroll
            for (int kk = 0; kk < 4; kk++) {
              const uint4 m = lds4(mt + i * 256 + kk * 64);
              f[4 * kk] = MODUL(f[4 * kk], m.x, m.z); f[4 * kk + 1] = MODUL(f[4 * kk + 1], m.x, m.z);
              f[4 * kk + 2] = MODUL(f[4 * kk + 2], m.y, m.w); f[4 * kk + 3] = MODUL(f[4 * kk + 3], m.y, m.w);
            }
            keep(f);
            mbar_arrive_pred(xempty + (i & 3) * 8, l == 0);
          };
          auto publish = [&](int u, uint32_t (&f)[16]) {
#pragma unroll
            for (int kk = 0; kk < 4; kk++) stmatrix4(fa[kk] + OFF_STAGE + u * UNIT, f[4 * kk], f[4 * kk + 1], f[4 * kk + 2], f[4 * kk + 3]);
            if (u == 1) { __syncwarp(); mbar_arrive_pred(bar_hpub, l == 0); }
          };
          auto multiply = [&](int i, uint32_t (&f)[16]) {
            mbar_wait(gfull + (i & 3) * 8, i >> 2);
            const uint64_t db = make_desc(base + (i & 3) * GST_BYTES + UNIT, 8192, 1024);
            wg_fence();
#pragma unroll
            for (int kk = 0; kk < 4; kk++) mma256_rs(ga, gb, f[4 * kk], f[4 * kk + 1], f[4 * kk + 2], f[4 * kk + 3], db + kk * 128);
            wg_commit();
          };
          auto next = [&](int i, uint32_t (&f)[16]) {
            wg_wait<1>();
            mbar_arrive_cl(rempty, GE + ((i + 2) & 3) * 8);
            mbar_wait(xfull + (i & 3) * 8, i >> 2);
#pragma unroll
            for (int kk = 0; kk < 4; kk++)
              asm volatile("{ .reg .pred p; setp.eq.u32 p, %5, 0; @p ldmatrix.sync.aligned.m8n8.x4.shared.b16 {%0,%1,%2,%3}, [%4]; }"
                           : "+r"(f[4 * kk]), "+r"(f[4 * kk + 1]), "+r"(f[4 * kk + 2]), "+r"(f[4 * kk + 3]) : "r"(fa[kk] + (i & 3) * GST_BYTES), "r"(zero) : "memory");
            normalize(f); modulate(i, f); multiply(i, f);
          };
          normalize(a[0]); normalize(a[1]);
          keep(a[0]); keep(a[1]);
          mbar_wait(bar_mod, 0);
          PROF(1, tid == 0, 2);
          if (PORD == 0) { modulate(0, a[0]); multiply(0, a[0]); modulate(1, a[1]); multiply(1, a[1]); publish(0, a[0]); publish(1, a[1]); }
          if (PORD == 1) { modulate(0, a[0]); multiply(0, a[0]); publish(0, a[0]); modulate(1, a[1]); multiply(1, a[1]); publish(1, a[1]); }
          if (PORD == 2) { modulate(0, a[0]); multiply(0, a[0]); publish(0, a[0]); modulate(1, a[1]); publish(1, a[1]); multiply(1, a[1]); }
#pragma unroll 1
          for (int i = 2; i < NRS; i += 2) { next(i, a[0]); next(i + 1, a[1]); }
          wg_wait<1>();
          mbar_arrive_cl(rempty, GE + ((NRS + 2) & 3) * 8);
#pragma unroll 1
          for (int i = NRS; i < 14; i++) {
            mbar_wait(xfull + (i & 3) * 8, (i >> 2) & 1);
            mbar_wait(gfull + (i & 3) * 8, (i >> 2) & 1);
            const uint32_t xa = base + (i & 3) * GST_BYTES;
            const uint64_t da = make_desc(xa + wg * 8192, 16, 1024), db = make_desc(xa + UNIT, 8192, 1024);
            if (i == 13) bar_sync(2 + wg, 256);
            wg_fence();
#pragma unroll
            for (int kk = 0; kk < 4; kk++) mma256_ss(ga, gb, da + kk * 2, db + kk * 128, 1);
            wg_commit();
            if (i == 13) bar_arrive(3 - wg, 256);
            wg_wait<1>();
            uint32_t z = zero;
#pragma unroll
            for (int k = 0; k < 16; k += 2) asm volatile("lop3.b32 %0, %1, %2, %0, 0xA8;" : "+r"(z) : "r"(a[1][k]), "r"(a[1][k + 1]));
            mbar_arrive_cl(rempty, GE + ((i + 3) & 3) * 8 + z);
            mbar_arrive_pred(xempty + ((i + 3) & 3) * 8, l == 0 && i != NRS);
          }
          mbar_wait(xfull + 16, 1);
          wg_wait<0>();
          keep(ga); keep(gb);
#pragma unroll
          for (int i = 0; i < 64; i++) {
            asm volatile("mov.b32 %0, %1;" : "=f"(s[i]) : "f"(ga[i]));
            asm volatile("mov.b32 %0, %1;" : "=f"(o[i]) : "f"(gb[i]));
          }
        } else {
          float ga[64], gb[64];
#pragma unroll
          for (int i = 0; i < 64; i++) {
            asm volatile("mov.b32 %0, %1;" : "=f"(ga[i]) : "f"(s[i]));
            asm volatile("mov.b32 %0, %1;" : "=f"(gb[i]) : "f"(o[i]));
          }
#pragma unroll 1
          for (int i = 0; i < nst; i++) {
            mbar_wait(gfull + (i & 3) * 8, (i >> 2) & 1);
            const uint64_t da = make_desc(base + unit_of(xt, i & 3) + wg * 8192, 16, 1024), db = make_desc(base + unit_of(wt, i & 3), 8192, 1024);
            if (i == nst - 1) bar_sync(2 + wg, 256);
            wg_fence();
#pragma unroll
            for (int kk = 0; kk < 4; kk++) mma256_ss(ga, gb, da + kk * 2, db + kk * 128, kk ? 1 : i);
            wg_commit();
            if (i == nst - 1) bar_arrive(3 - wg, 256);
            wg_wait<1>();
            mbar_arrive_cl(rempty, GE + ((i + 3) & 3) * 8, i != 0);
            PROF(4, tid == 0 && (i & 3) == 0, 40 + (ps - 1) * 4 + i / 4);
          }
          wg_wait<0>();
          keep(ga); keep(gb);
#pragma unroll
          for (int i = 0; i < 64; i++) {
            asm volatile("mov.b32 %0, %1;" : "=f"(s[i]) : "f"(ga[i]));
            asm volatile("mov.b32 %0, %1;" : "=f"(o[i]) : "f"(gb[i]));
          }
        }
        mbar_arrive_cl(rempty, GE + (ps == 2 ? 24 : 8));
        if (ps == 2) break;
      }
      const uint32_t qw = base + wg * 8192, qt = QT >> (16 * ps), at = ps ? AT1 : AT0;
      {
        const uint32_t wt = ps ? WT1 : WT0;
        const uint64_t da0 = make_desc(qw + unit_of(qt, 2), 16, 1024), da1 = make_desc(qw + unit_of(qt, 3), 16, 1024);
        const uint64_t db0 = make_desc(base + unit_of(wt, 2), 8192, 1024), db1 = make_desc(base + unit_of(wt, 3), 8192, 1024);
        mbar_wait(gfull + 16, 1);
        bar_sync(2 + wg, 256);
        wg_fence();
#pragma unroll
        for (int kk = 0; kk < 4; kk++) mma_ss<1>(s, da0 + kk * 2, db0 + kk * 128, 1);
        wg_commit();
        mbar_wait(xfull + 24, 1);
        mbar_wait(gfull + 24, 1);
        wg_fence();
#pragma unroll
        for (int kk = 0; kk < 4; kk++) mma_ss<1>(s, da1 + kk * 2, db1 + kk * 128, 1);
        wg_commit();
        bar_arrive(3 - wg, 256);
        mbar_wait(ps == 0 ? bar_pread : bar_ofree + 8, 0);
        mbar_wait(bfull, 0);
        wg_wait<0>();
        keep(s);
        PROF(2, tid == 0, 8 + ps * 8);
        store_chunk<0>(s, qw + unit_of(qt, 0) + frag_offset(warp));
        store_chunk<1>(s, qw + unit_of(qt, 1) + frag_offset(warp));
        fence_async_smem();
        bar_sync(2 + wg, 256);
        wg_fence();
        issue_qk(s, qw + unit_of(qt, 0), qw + unit_of(qt, 1), base + unit_of(at, 0));
        wg_commit();
#pragma unroll
        for (int kk = 0; kk < 8; kk++) mma_ss<1>(o, (kk < 4 ? da0 : da1) + (kk & 3) * 2, (kk < 4 ? db0 : db1) + UNIT / 16 + (kk & 3) * 128, 1);
        wg_commit();
        bar_arrive(3 - wg, 256);
        wg_wait<1>();
        keep(s);
        mbar_arrive_cl(rempty, 0);
      }
      PROF(4, tid == 0 && ps == 1, 61);
      float l0 = 0.25f, l1 = 0.25f;
      auto step = [&](auto odd_c, const int j, uint32_t (&pw)[32], uint32_t (&pr)[32]) {
        constexpr bool ODD = decltype(odd_c)::value;
        const bool first = !ODD && (j & 2) == 0, last = ODD && j == 7;
        const uint32_t ph = (j >> 1) & 1;
        float i0, i1, a0, a1;
        if (first) { i0 = inv_quad_sum(l0); i1 = inv_quad_sum(l1); l0 = 0.f; l1 = 0.f; }
        bool redo = !ODD && (j | ps) == 0, again = false;
        while (true) {
          if (redo) {
            float m0 = fmaxf(s[0], s[1]), m1 = fmaxf(s[2], s[3]);
#pragma unroll
            for (int i = 1; i < 16; i++) { m0 = fmaxf(m0, fmaxf(s[4 * i], s[4 * i + 1])); m1 = fmaxf(m1, fmaxf(s[4 * i + 2], s[4 * i + 3])); }
            m0 = fmaxf(m0, __shfl_xor_sync(0xffffffffu, m0, 1)); m1 = fmaxf(m1, __shfl_xor_sync(0xffffffffu, m1, 1));
            m0 = fmaxf(m0, __shfl_xor_sync(0xffffffffu, m0, 2)); m1 = fmaxf(m1, __shfl_xor_sync(0xffffffffu, m1, 2));
            m0 *= SCL2; m1 *= SCL2;
            if (!first) {
              m0 = fmaxf(m0, f0); m1 = fmaxf(m1, f1);
              const float c0 = ex2(f0 - m0), c1 = ex2(f1 - m1);
              l0 *= c0; l1 *= c1;
              wg_wait<0>();
              keep(o);
#pragma unroll
              for (int i = 0; i < 16; i++) { o[4 * i] *= c0; o[4 * i + 1] *= c0; o[4 * i + 2] *= c1; o[4 * i + 3] *= c1; }
            }
            f0 = m0; f1 = m1;
          }
          float b0 = 0.f, b1 = 0.f;
          a0 = 0.f; a1 = 0.f;
#pragma unroll
          for (int i = 0; i < 16; i++) {
            const float e0 = ex2(fmaf(s[4 * i], SCL2, -f0)), e1 = ex2(fmaf(s[4 * i + 1], SCL2, -f0));
            const float e2 = ex2(fmaf(s[4 * i + 2], SCL2, -f1)), e3 = ex2(fmaf(s[4 * i + 3], SCL2, -f1));
            a0 += e0; b0 += e1; a1 += e2; b1 += e3;
            pw[2 * i] = pack_bf(e0, e1); pw[2 * i + 1] = pack_bf(e2, e3);
            if (i == VREL) {
#pragma unroll
              for (int k = 0; k < 2 * VREL + 2; k++) asm volatile("" : "+r"(pw[k])::"memory");
              mbar_wait(bar_mod, 0);
              wg_wait<0>();
              mbar_arrive_cl(rempty, ODD ? 16 : (j ? 0 : GE + 16), !again);
              if (!ODD) mbar_arrive_cl(rempty, GE + 24, !again && j == 0);
#pragma unroll
              for (int k = 4 * VREL + 4; k < 64; k++) asm volatile("" : "+f"(s[k])::"memory");
            }
          }
          a0 += b0; a1 += b1;
          if (redo) break;
          redo = __any_sync(0xffffffffu, !(a0 + a1 < 0x1p70f));
          if (first) {
            uint32_t m0 = __ballot_sync(0xffffffffu, a0 > 0x1p-50f), m1 = __ballot_sync(0xffffffffu, a1 > 0x1p-50f);
            m0 |= m0 >> 1; m1 |= m1 >> 1; m0 |= m0 >> 2; m1 |= m1 >> 2;
            redo = redo || (m0 & m1 & 0x11111111u) != 0x11111111u;
          }
          if (!redo) break;
          again = true;
        }
        l0 += a0; l1 += a1;
        keep(pw);
        keep(o);
        const uint32_t qo = qt >> (j ? 0 : 8);
        if (first) store_chunk<0>(o, i0, i1, qw + unit_of(qo, 0) + frag_offset(warp));
        keep(o);
        mbar_wait(bfull + (ODD ? 24 : 8), ph);
        bar_sync(2 + wg, 256);
        if (!last) {
          const uint32_t qn = qt >> (j >= 3 ? 8 : 0);
          wg_fence();
          issue_qk(s, qw + unit_of(qn, 0), qw + unit_of(qn, 1), base + unit_of(at, ODD ? 3 : 1));
          wg_commit();
          mbar_wait(bfull + (ODD ? 0 : 16), ODD ? ph ^ 1 : ph);
        }
        if (first) { store_chunk<1>(o, i0, i1, qw + unit_of(qo, 1) + frag_offset(warp)); keep(o); }
        wg_fence();
        issue_pv(o, pw, base + unit_of(at, ODD ? (last ? 3 : 0) : 2), !first);
        wg_commit();
        bar_arrive(3 - wg, 256);
        wg_wait<1>();
        keep(s);
        mbar_arrive_cl(rempty, ODD ? 24 : 8, !last);
        if (first) { fence_async_smem(); mbar_arrive_pred(bar_ofull + wg * 8, j); }
        PROF(4, tid == 0 && ps == 1, 51 + j);
      };
      uint32_t pa[32], pb[32];
#pragma unroll 1
      for (int j = 0; j < 8; j += 2) {
        step(std::false_type{}, j, pa, pb);
        step(std::true_type{}, j + 1, pb, pa);
      }
      {
        const float i0 = inv_quad_sum(l0), i1 = inv_quad_sum(l1);
        wg_wait<0>();
        keep(o);
        mbar_arrive_cl(rempty, 24);
        store_chunk<0>(o, i0, i1, qw + unit_of(qt, 2) + frag_offset(warp));
        store_chunk<1>(o, i0, i1, qw + unit_of(qt, 3) + frag_offset(warp));
        fence_async_smem();
        mbar_arrive(bar_ofull + 16 + wg * 8);
      }
      PROF(2, tid == 0, 10 + ps * 8);
    }

    const int ln = fresh_lane(), g = ln >> 2, tq = ln & 3, ct = warp * 32 + ln;
    const bool lane0 = ln == 0;
    const int lrow0 = warp * 16 + g;
    const int grow0 = rb * 128 + lrow0;
    const uint32_t res = base + OFF_RES, trow = res + wg * 8192 + frag_offset(warp);
    uint32_t xr[32];
    uint4 sv[4], own;
    uint32_t* sp[4];
#pragma unroll
    for (int k = 0; k < 4; k++) sp[k] = g_stats + ((((tq >> 1) * 4 + k) ^ cj) * SEQ + grow0 + (tq & 1) * 8) * 4;
    {
      const uint64_t da = make_desc(base + wg * 8192, 16, 1024), db = make_desc(base, 8192, 1024);
      constexpr int U = UNIT / 16;
#define HALF_STAGE(acc, xu, wu) _Pragma("unroll") for (int kk = 0; kk < 4; kk++) mma_ss<1>(acc, da + (xu) * U + kk * 2, db + (wu) * U + kk * 128, 1)
      PROF(10, ct == PT, 19); STAMP(0);
      cluster_arrive();
      mbar_wait(gfull, 1);
      mbar_wait(gfull + 8, 1);
      bar_sync(2 + wg, 256);
      wg_fence();
      HALF_STAGE(o, 7, 1);
      HALF_STAGE(o, 8, 3);
      wg_commit();
      STAMP(16);
      mbar_wait(gfull + 16, 1);
      STAMP(17);
      wg_fence();
      HALF_STAGE(o, 6, 11);
      wg_commit();
      bar_arrive(3 - wg, 256);
      mbar_wait(bar_par, 0);
      uint32_t* xo = g_xch + ((size_t)b * 8 * 256 + ct) * 4;
      const uint32_t* xi = g_xch + ((size_t)(b ^ 2) * 8 * 256 + ct) * 4;
      const uint32_t par1 = (~lds1(par + PAR_CONST + 4) & 1) << 16;
      uint32_t ga[16];
      uint4 bw[8];
#define LOAD_PAR _Pragma("unroll") for (int i = 0; i < 8; i++) {                                                               \
        ga[2 * i] = lds1(par + PAR_T2 + i * 128 + tq * 16 + 12); ga[2 * i + 1] = lds1(par + PAR_T2 + i * 128 + 64 + tq * 16 + 12); \
        bw[i] = lds4(par + PAR_T1 + i * 64 + tq * 16);                                                                          \
        if (!(g & 1)) { bw[i].x = 0x3f803f80u; bw[i].y = 0x3f803f80u; }                                                         \
      }
      if (PPOS == 0) LOAD_PAR
      wg_wait<1>();
      mbar_arrive_pred(bar_rel, lane0);
      wg_wait<0>();
      keep(o);
      mbar_arrive_pred(bar_ring, lane0);
      PROF(8, ct == PT, 20); STAMP(1);
#define SEND(i) st_b128(xo + (i) * 1024, (pack_bf(o[8 * (i)], o[8 * (i) + 1]) & ~0x10000u) | par1, pack_bf(o[8 * (i) + 2], o[8 * (i) + 3]), \
                        pack_bf(o[8 * (i) + 4], o[8 * (i) + 5]), pack_bf(o[8 * (i) + 6], o[8 * (i) + 7]))
#pragma unroll
      for (int i = 0; i < NS1; i++) SEND(i);
      PROF(8, ct == PT, 21); STAMP(2);
      bar_sync(2 + wg, 256);
      wg_fence();
      HALF_STAGE(s, 7, 0);
      HALF_STAGE(s, 8, 2);
      HALF_STAGE(s, 6, 10);
      wg_commit();
      bar_arrive(3 - wg, 256);
      STAMP(18);
      mbar_wait(gfull + 24, 1);
#pragma unroll
      for (int i = NS1; i < 8; i++) SEND(i);
      uint4 v[8];
#pragma unroll
      for (int i = 0; i < 4; i++) v[i] = ld_b128(xi + i * 1024);
      if (PPOS == 1) LOAD_PAR
      STAMP(19);
      mbar_wait(bar_xres, 0);
      wg_wait<0>();
      mbar_arrive_pred(bar_ring + 8, lane0);
      bar_sync(2 + wg, 256);
      STAMP(20);
#pragma unroll
      for (int i = 4; i < 8; i++) v[i] = ld_b128(xi + i * 1024);
      mbar_wait(bar_xres, 0);
      wg_fence();
      HALF_STAGE(s, 9, 4);
      wg_commit();
      mbar_wait(bar_rx, 0);
      wg_fence();
      HALF_STAGE(s, 1, 5);
      wg_commit();
      bar_arrive(3 - wg, 256);
      STAMP(21);
      wg_wait<0>();
      keep(s);
      mbar_arrive_pred(bar_ring + 16, lane0);
      PROF(10, ct == PT, 23); STAMP(4);
#pragma unroll
      for (int i = 0; i < 16; i += 2) ldmatrix4((trow ^ ((i & 7) << 4)) + (i >> 3) * 16384, xr[2 * i], xr[2 * i + 1], xr[2 * i + 2], xr[2 * i + 3]);
      if (PPOS == 2) LOAD_PAR
      uint32_t pk[32];
      pack_p(s, pk);
      keep(pk);
      {
        uint32_t n = 0, miss;
        do {
          miss = 0;
#pragma unroll
          for (int i = 0; i < 8; i++) miss |= v[i].x ^ par1;
          miss = __any_sync(0xffffffffu, miss & 0x10000u);
          if (miss) {
#pragma unroll
            for (int i = 0; i < 8; i++)
              asm volatile("{ .reg .pred p; .reg .b32 t; xor.b32 t, %0, %5; and.b32 t, t, 0x10000; setp.ne.u32 p, t, 0;\n"
                           "@p ld.relaxed.gpu.global.v4.u32 {%0, %1, %2, %3}, [%4]; }"
                           : "+r"(v[i].x), "+r"(v[i].y), "+r"(v[i].z), "+r"(v[i].w) : "l"(xi + i * 1024), "r"(par1) : "memory");
          }
          watchdog(n);
        } while (miss);
      }
      PROF(8, ct == PT, 22); STAMP(3);
#pragma unroll
      for (int k = 0; k < 4; k++) sv[k] = ESV ? ld_b128(sp[k]) : make_uint4(0, 0, 0, 0);
      float ds[4] = {0.f, 0.f, 0.f, 0.f}, dl[4] = {0.f, 0.f, 0.f, 0.f}, q0[4] = {0.f, 0.f, 0.f, 0.f}, q1[4] = {0.f, 0.f, 0.f, 0.f};
#pragma unroll
      for (int i = 0; i < 8; i++) {
        const uint32_t u0 = hfma2(ga[2 * i], hadd2(pk[4 * i], v[i].x & ~0x10000u), xr[4 * i]);
        const uint32_t u1 = hfma2(ga[2 * i], hadd2(pk[4 * i + 1], v[i].y), xr[4 * i + 1]);
        const uint32_t u2 = hfma2(ga[2 * i + 1], hadd2(pk[4 * i + 2], v[i].z), xr[4 * i + 2]);
        const uint32_t u3 = hfma2(ga[2 * i + 1], hadd2(pk[4 * i + 3], v[i].w), xr[4 * i + 3]);
        xr[4 * i] = u0; xr[4 * i + 1] = u1; xr[4 * i + 2] = u2; xr[4 * i + 3] = u3;
        mma16816(ds, u0, u1, u2, u3, bw[i].x, bw[i].y);
        mma16816(dl, u0, u1, u2, u3, bw[i].z, bw[i].w);
        mma16816(q0, u0, u1, u2, u3, u0, u2);
        mma16816(q1, u0, u1, u2, u3, u1, u3);
      }
      const float sqa = __shfl_sync(0xffffffffu, (g & 1) ? q0[1] : q0[0], g * 4 + (g >> 1));
      const float sqb = __shfl_sync(0xffffffffu, (g & 1) ? q1[3] : q1[2], g * 4 + (g >> 1));
      own = (tq & 1) ? make_uint4(__float_as_uint(ds[2]), __float_as_uint(sqb), __float_as_uint(ds[3] + dl[3]), tag)
                                 : make_uint4(__float_as_uint(ds[0]), __float_as_uint(sqa), __float_as_uint(ds[1] + dl[1]), tag);
      if (tq < 2) st_b128(sp[0], own.x, own.y, own.z, own.w);
    }
    PROF(8, ct == PT, 29); STAMP(5);
    uint32_t mm, ih, il;
    float rbest;
    uint32_t wf[128];
    const uint32_t frow = (ln & 7) + (ln >> 4) * 8;
    const uint32_t wfo = base + (warp & 1) * 8192 + frow * 64 + ((((ln >> 3) & 1) ^ ((frow >> 1) & 3)) << 4);
#define LOAD_WF(m) _Pragma("unroll") for (int f = 0; f < 16; f++) {                                                   \
      const int r = ((f >> 1) * 4 + (m) * 2 + (f & 1)) * 4;                                                           \
      ldmatrix4t(((wfo + unit_of((m) ? FT_U : FT_G, warp >> 1)) ^ ((f & 1) * 32)) + (f >> 1) * 1024, wf[r], wf[r + 1], wf[r + 2], wf[r + 3]); \
    }
    bool early, wait1;
    {
#pragma unroll
      for (int i = 0; i < 16; i += 2) stmatrix4((trow ^ ((i & 7) << 4)) + (i >> 3) * 16384, xr[2 * i], xr[2 * i + 1], xr[2 * i + 2], xr[2 * i + 3]);
      const uint4 cst = lds4(par + PAR_CONST);
      const float A1 = __uint_as_float(cst.x), A2 = __uint_as_float(cst.z);
      uint32_t n = 0;
      early = false; wait1 = false;
#pragma unroll 1
      while (true) {
        uint32_t miss;
        asm volatile("{ .reg .pred p0, p1, p2, p3; .reg .b64 u, v; .reg .b128 w;\n"
                     "setp.ge.u32 p0, %22, 2; setp.ne.and.u32 p0, %4, %21, p0; setp.ne.u32 p1, %8, %21; setp.ne.u32 p2, %12, %21; setp.ne.u32 p3, %16, %21;\n"
                     "@p0 ld.relaxed.gpu.global.v4.u32 {%1, %2, %3, %4}, [%17];\n"
                     "@p1 ld.relaxed.gpu.global.v4.u32 {%5, %6, %7, %8}, [%18];\n"
                     "@p2 ld.relaxed.gpu.global.v4.u32 {%9, %10, %11, %12}, [%19];\n"
                     "@p3 ld.relaxed.gpu.global.v4.u32 {%13, %14, %15, %16}, [%20];\n"
                     "or.pred p0, p0, p1; or.pred p2, p2, p3; or.pred p0, p0, p2; vote.sync.any.pred p0, p0, 0xffffffff; selp.u32 %0, 1, 0, p0; }"
                     : "=r"(miss), "+r"(sv[0].x), "+r"(sv[0].y), "+r"(sv[0].z), "+r"(sv[0].w), "+r"(sv[1].x), "+r"(sv[1].y), "+r"(sv[1].z), "+r"(sv[1].w),
                       "+r"(sv[2].x), "+r"(sv[2].y), "+r"(sv[2].z), "+r"(sv[2].w), "+r"(sv[3].x), "+r"(sv[3].y), "+r"(sv[3].z), "+r"(sv[3].w)
                     : "l"(sp[0]), "l"(sp[1]), "l"(sp[2]), "l"(sp[3]), "r"(tag), "r"(tq) : "memory");
        if (!miss) break;
        wait1 = true;
        if (!early && (b >= NFFN || __all_sync(0xffffffffu, mbar_test(bar_box + (warp >> 1) * 8, 0)))) {
          early = true;
          LOAD_WF(0);
          __syncwarp();
          mbar_arrive_pred(bar_gate, lane0);
        }
        watchdog(n);
      }
      const uint4 v0 = tq < 2 ? own : sv[0], v1 = sv[1], v2 = sv[2], v3 = sv[3];
      PROF(8, ct == PT, 30); STAMP(6);
      float su = (__uint_as_float(v0.x) + __uint_as_float(v1.x)) + (__uint_as_float(v2.x) + __uint_as_float(v3.x));
      float sq = (__uint_as_float(v0.y) + __uint_as_float(v1.y)) + (__uint_as_float(v2.y) + __uint_as_float(v3.y));
      float dt = (__uint_as_float(v0.z) + __uint_as_float(v1.z)) + (__uint_as_float(v2.z) + __uint_as_float(v3.z));
      su += __shfl_xor_sync(0xffffffffu, su, 2); sq += __shfl_xor_sync(0xffffffffu, sq, 2); dt += __shfl_xor_sync(0xffffffffu, dt, 2);
      const float m = su * (1.f / DM);
      float mb, sd;
      ln_scalars(m, fmaxf(sq * (1.f / DM) - m * m, 0.f), mb, sd);
      const float inv = rcp(sd);
      rbest = (dt - mb * A1) * inv + A2;
      mm = pack_bf(mb, mb);
      ih = pack_bf(inv, inv);
      const float lo = inv - bf_lo(ih);
      il = pack_bf(lo, lo);
    }
    int ibest;
    {
      const uint32_t bits = __float_as_uint(rbest);
      const uint32_t key = (((int)bits < 0 ? ~bits : bits | 0x80000000u) & ~0x1ffu) | ((127 - lrow0 - (tq & 1) * 8) << 2) | tag;
      sts1(par + PAR_RED + warp * 4, __reduce_max_sync(0xffffffffu, key));
      PROF(8, ct == PT, 38); STAMP(7);
      uint32_t waited;
      asm volatile("{ .reg .pred p, q; setp.ne.u32 p, %1, 0; barrier.cta.red.or.pred q, 1, 256, p; selp.u32 %0, 1, 0, q; }" : "=r"(waited) : "r"((uint32_t)(wait1 && (wg || CW0))) : "memory");
      const uint4 ka = lds4(par + PAR_RED), kb = lds4(par + PAR_RED + 16);
      const uint32_t k2 = max(max(max(ka.x, ka.y), max(ka.z, ka.w)), max(max(kb.x, kb.y), max(kb.z, kb.w)));
      if (ct == 0 && ((cj & CWM) == 0 || (CWL && !waited))) st_relaxed(g_cand + rb, k2);
      ibest = 127 - ((k2 >> 2) & 127);
    }
    PROF(8, ct == PT, 39); STAMP(8);
    if ((ibest >> 4) == warp) {
      const int src = (ibest & 7) * 4 + ((ibest >> 3) & 1), ch = g * 2;
      const uint32_t cm = __shfl_sync(0xffffffffu, mm, src), ch_ = __shfl_sync(0xffffffffu, ih, src), cl = __shfl_sync(0xffffffffu, il, src);
      const uint32_t xa = res + (ch >> 3) * 16384 + ibest * 128 + (((ch & 7) ^ (ibest & 7)) << 4) + tq * 4;
      const uint32_t x0 = lds1(xa), x1 = lds1(xa ^ 16);
      const uint2 p0 = lds2(par + PAR_T2 + ch * 64 + tq * 16), p1 = lds2(par + PAR_T2 + ch * 64 + 64 + tq * 16);
      uint32_t* dst = g_row + rb * 2 * DM + cj * 128 + ln * 4;
      st_pairs(dst, ln_mod(x0, cm, ch_, cl, p0.x, p0.y), ln_mod(x1, cm, ch_, cl, p1.x, p1.y), tag);
      st_pairs(dst + DM, x0, x1, tag);
      __syncwarp();
    }
    PROF(8, ct == PT, 37); STAMP(9);
    uint32_t wd[64];
    const uint32_t wda = base + unit_of(FT_D, warp >> 1) + (warp & 1) * 8192 + frow * 128 + ((((ln >> 3) & 1) ^ (ln & 7)) << 4);
#define LOAD_WD(f) ldmatrix4t((wda ^ ((((f) >> 1) & 3) * 32)) + ((f) >> 3) * 4096 + ((f) & 1) * 2048, wd[4 * (f)], wd[4 * (f) + 1], wd[4 * (f) + 2], wd[4 * (f) + 3])
    if (!early) {
      if (b < NFFN) mbar_wait(bar_box + (warp >> 1) * 8, 0);
      LOAD_WF(0);
      __syncwarp();
      mbar_arrive_pred(bar_gate, lane0);
    }
    if (b < NFFN) {
      const uint32_t own = base + unit_of(FT_G, warp >> 1) + (warp & 1) * 8192;
      mbar_wait(bar_box + (4 + (warp >> 1)) * 8, 0);
      LOAD_WF(1);
      uint32_t* const ydst = g_ypart + ((size_t)(warp * 16 + tq * 2) * NFFN + b) * 8 + g;
      PROF(8, ct == PT, 31); STAMP(10);
      mbar_wait(bar_box + (8 + (warp >> 1)) * 8, 0);
#pragma unroll
      for (int f = 0; f < WDE; f++) LOAD_WD(f);
      STAMP(11);
      mbar_wait(bar_sel, 0);
      PROF(8, ct == PT, 33); STAMP(12);
      float d[8][4];
#pragma unroll
      for (int i = 0; i < 4; i++) { d[i][0] = 0.f; d[i][1] = 0.f; d[i][2] = 0.f; d[i][3] = 0.f; }
#pragma unroll
      for (int ks = 0; ks < 8; ks++) {
        const uint2 hb = lds2(own + 256 + ks * 32 + tq * 8);
#pragma unroll
        for (int mt = 0; mt < 4; mt++) {
          const int r = ks * 16 + mt * 4;
          mma16816(d[mt], wf[r], wf[r + 1], wf[r + 2], wf[r + 3], hb.x, hb.y);
        }
      }
      sts2(own + (tq * 8 + g) * 8, __float_as_uint((tq & 2) ? ((tq & 1) ? d[1][2] : d[1][0]) : ((tq & 1) ? d[0][2] : d[0][0])),
           __float_as_uint((tq & 2) ? ((tq & 1) ? d[3][2] : d[3][0]) : ((tq & 1) ? d[2][2] : d[2][0])));
      bar_sync(1, 256);
      uint32_t ab[4];
      {
        float G = 0.f, U = 0.f;
        uint2 pv[8];
#pragma unroll
        for (int w8 = 0; w8 < 8; w8++) pv[w8] = lds2(base + ln * 8 + ((FT_G >> (w8 >> 1) * 4) & 15) * UNIT + (w8 & 1) * 8192);
#pragma unroll
        for (int w8 = 0; w8 < 8; w8 += 2) {
          G += __uint_as_float(pv[w8].x) + __uint_as_float(pv[w8 + 1].x);
          U += __uint_as_float(pv[w8].y) + __uint_as_float(pv[w8 + 1].y);
        }
#pragma unroll
        for (int f = WDE; f < 16; f++) LOAD_WD(f);
        const float act = rbf(silu_f(rbf(G))) * rbf(U);
        const uint32_t pk = pack_bf(act, __shfl_down_sync(0xffffffffu, act, 1));
#pragma unroll
        for (int i = 0; i < 4; i++) ab[i] = __shfl_sync(0xffffffffu, pk, i * 8 + tq * 2);
      }
      PROF(8, ct == PT, 34); STAMP(13);
#pragma unroll
      for (int mt = 0; mt < 8; mt++) {
        d[mt][0] = 0.f; d[mt][1] = 0.f; d[mt][2] = 0.f; d[mt][3] = 0.f;
        mma16816(d[mt], wd[mt * 8], wd[mt * 8 + 1], wd[mt * 8 + 2], wd[mt * 8 + 3], ab[0], ab[1]);
        mma16816(d[mt], wd[mt * 8 + 4], wd[mt * 8 + 5], wd[mt * 8 + 6], wd[mt * 8 + 7], ab[2], ab[3]);
      }
#pragma unroll
      for (int i = 0; i < 4; i++) {
        const int m4 = (i >> 1) * 4, e = (i & 1) * 2;
        const float y = (tq & 2) ? ((tq & 1) ? d[m4 + 3][e] : d[m4 + 2][e]) : ((tq & 1) ? d[m4 + 1][e] : d[m4][e]);
        st_relaxed(ydst + (m4 * 2 + (i & 1)) * NFFN * 8, tagf(y, tag));
      }
      PROF(8, ct == PT, 35); STAMP(14);
    }
    mbar_wait(bar_sel, 0);
    mbar_arrive_pred(bar_win, ct == 0);
    const int iwin = lds1(par + PAR_CONST + 60) & 0x7ff;
    {
      const uint32_t mm0 = __shfl_sync(0xffffffffu, mm, ln & ~1), mm1 = __shfl_sync(0xffffffffu, mm, ln | 1);
      const uint32_t ih0 = __shfl_sync(0xffffffffu, ih, ln & ~1), ih1 = __shfl_sync(0xffffffffu, ih, ln | 1);
      const uint32_t il0 = __shfl_sync(0xffffffffu, il, ln & ~1), il1 = __shfl_sync(0xffffffffu, il, ln | 1);
      const bool mine = (iwin >> 4) == rb * 8 + warp;
#pragma unroll 1
      for (int hf = 0; hf < 2; hf++) {
        uint32_t x[16];
#pragma unroll
        for (int i = 0; i < 8; i += 2) ldmatrix4((trow ^ (i << 4)) + hf * 16384, x[2 * i], x[2 * i + 1], x[2 * i + 2], x[2 * i + 3]);
#pragma unroll
        for (int i = 0; i < 8; i++) {
          const uint4 pv = lds4(par + PAR_T2 + (hf * 8 + i) * 64 + tq * 16);
          x[2 * i] = hadd2(x[2 * i], hmul2(pv.z, ln_mod(x[2 * i], mm0, ih0, il0, pv.x, pv.y)));
          x[2 * i + 1] = hadd2(x[2 * i + 1], hmul2(pv.z, ln_mod(x[2 * i + 1], mm1, ih1, il1, pv.x, pv.y)));
        }
        if (mine) {
          uint32_t* dst = reinterpret_cast<uint32_t*>(P.out + (size_t)grow0 * DM + cj * 128 + hf * 64) + tq;
#pragma unroll
          for (int i = 0; i < 8; i++) {
            if (grow0 != iwin) dst[i * 4] = x[2 * i];
            if (grow0 + 8 != iwin) dst[i * 4 + 4 * DM] = x[2 * i + 1];
          }
        } else {
#pragma unroll
          for (int i = 0; i < 8; i += 2) stmatrix4((trow ^ (i << 4)) + hf * 16384, x[2 * i], x[2 * i + 1], x[2 * i + 2], x[2 * i + 3]);
          fence_async_smem();
          __syncwarp();
          if (elect_one()) {
            tma2d_store(&maps.out, res + hf * 16384 + warp * 2048, cj * 128 + hf * 64, rb * 128 + warp * 16);
            asm volatile("cp.async.bulk.commit_group;" ::: "memory");
          }
        }
      }
      asm volatile("cp.async.bulk.wait_group.read 0;" ::: "memory");
    }
    PROF(8, ct == PT, 11); STAMP(15);
    cluster_wait();
  }
}

typedef CUresult (*EncodeFn)(CUtensorMap*, CUtensorMapDataType, cuuint32_t, void*, const cuuint64_t*, const cuuint64_t*,
                             const cuuint32_t*, const cuuint32_t*, CUtensorMapInterleave, CUtensorMapSwizzle,
                             CUtensorMapL2promotion, CUtensorMapFloatOOBfill);

void map2d(EncodeFn enc, CUtensorMap* m, const void* p, uint64_t rows, uint64_t cols, uint32_t brows) {
  cuuint64_t dims[2] = {cols, rows}, strides[1] = {cols * 2};
  cuuint32_t box[2] = {64, brows}, es[2] = {1, 1};
  enc(m, CU_TENSOR_MAP_DATA_TYPE_BFLOAT16, 2, const_cast<void*>(p), dims, strides, box, es, CU_TENSOR_MAP_INTERLEAVE_NONE,
      CU_TENSOR_MAP_SWIZZLE_128B, CU_TENSOR_MAP_L2_PROMOTION_L2_256B, CU_TENSOR_MAP_FLOAT_OOB_FILL_NONE);
}
void map2d_narrow(EncodeFn enc, CUtensorMap* m, const void* p, uint64_t rows, uint64_t cols, uint32_t brows) {
  cuuint64_t dims[2] = {cols, rows}, strides[1] = {cols * 2};
  cuuint32_t box[2] = {32, brows}, es[2] = {1, 1};
  enc(m, CU_TENSOR_MAP_DATA_TYPE_BFLOAT16, 2, const_cast<void*>(p), dims, strides, box, es, CU_TENSOR_MAP_INTERLEAVE_NONE,
      CU_TENSOR_MAP_SWIZZLE_64B, CU_TENSOR_MAP_L2_PROMOTION_L2_64B, CU_TENSOR_MAP_FLOAT_OOB_FILL_NONE);
}
void map3d(EncodeFn enc, CUtensorMap* m, const void* p, uint64_t rows, uint64_t cols, uint32_t brows, uint32_t nch) {
  cuuint64_t dims[3] = {64, rows, cols / 64}, strides[2] = {cols * 2, 128};
  cuuint32_t box[3] = {64, brows, nch}, es[3] = {1, 1, 1};
  enc(m, CU_TENSOR_MAP_DATA_TYPE_BFLOAT16, 3, const_cast<void*>(p), dims, strides, box, es, CU_TENSOR_MAP_INTERLEAVE_NONE,
      CU_TENSOR_MAP_SWIZZLE_128B, CU_TENSOR_MAP_L2_PROMOTION_L2_256B, CU_TENSOR_MAP_FLOAT_OOB_FILL_NONE);
}

}

extern "C" void kernel_launch(void* const* d_in, const int* in_sizes, int n_in, void* d_out, int out_size) {
  (void)in_sizes; (void)n_in; (void)out_size;
  static EncodeFn enc = nullptr;
  if (!enc) {
    void* fn = nullptr;
    cudaDriverEntryPointQueryResult st;
    cudaGetDriverEntryPoint("cuTensorMapEncodeTiled", &fn, cudaEnableDefault, &st);
    enc = (EncodeFn)fn;
    cudaFuncSetAttribute(fused_kernel, cudaFuncAttributeMaxDynamicSharedMemorySize, SMEM_BYTES);
  }
  Maps maps;
  map2d(enc, &maps.x, d_in[0], SEQ, DM, 128);
  map2d(enc, &maps.out, d_out, SEQ, DM, 16);
  map3d(enc, &maps.wq, d_in[3], DM, NQ, 64, 2);
  map3d(enc, &maps.k, d_in[1], 4 * SK, 128, 128, 1);
  map3d(enc, &maps.v, d_in[2], 4 * SK, 128, 128, 1);
  map3d(enc, &maps.wo, d_in[4], NQ, DM, 64, 2);
  map2d_narrow(enc, &maps.wg, d_in[7], DM, FF, 256);
  map2d_narrow(enc, &maps.wu, d_in[8], DM, FF, 256);
  map3d(enc, &maps.wd, d_in[9], FF, DM, 32, 4);
  map2d_narrow(enc, &maps.wm, d_in[11], DM, NMOD, 256);
  Ptrs p;
  p.x = (const __nv_bfloat16*)d_in[0];
  p.w_r = (const __nv_bfloat16*)d_in[6];
  p.w_gate = (const __nv_bfloat16*)d_in[7];
  p.w_up = (const __nv_bfloat16*)d_in[8];
  p.w_down = (const __nv_bfloat16*)d_in[9];
  p.c = (const __nv_bfloat16*)d_in[10];
  p.w_mod = (const __nv_bfloat16*)d_in[11];
  p.out = (__nv_bfloat16*)d_out;
  fused_kernel<<<NMAIN + NHELP, 384, SMEM_BYTES>>>(maps, p);
}
```

```cpp
#include <cuda_runtime.h>
#include <cuda_bf16.h>
#include <cuda.h>
#include <stdint.h>
#include <type_traits>

#define HD 2
#define HDX 2
#define XF 4
#define XE 32
#define XR 0
#define NRS 8
#define FPACE 3
#define GOST 20
#define WB 3
#define WN 24
#define RES0 17
#define RES1 20
#define HU 32
#define NS1 6
#define PG0 0
#define PSL 0
#define CWM 7
#define WDE 16
#define CWL 1
#define CW0 0
#define ESV 1
#define PPOS 1
#define FB0 0
#define FB2 8
#define OPS 8192
#define OFL 0
#define ODS 8
#define PORD 0
#define MODUL hfma2
#define HCP 2
#define VREL 7
#define E0 3

namespace {

constexpr int SEQ = 2048, DM = 1024, NQ = 4096, SK = 2048, WIN = 512, FF = 3584, NMOD = 6144;
constexpr int NMAIN = 128, NHELP = 4, NFFN = 112;
constexpr int NSLOT = 4, SLOT_BYTES = 32768, UNIT = 16384, GST_BYTES = 3 * UNIT;
constexpr uint32_t XT1 = 0xDCBA, XT2 = 0x9687;
constexpr uint32_t WT0 = 0xA741, WT1 = 0x7420, WT2 = 0x4A20;
constexpr uint32_t AT0 = WT1, AT1 = WT2;
constexpr uint32_t QT = 0xDC9696DC;
constexpr int OFF_STAGE = 12 * UNIT;
constexpr uint32_t FT_G = 0x07B3, FT_U = 0xA628, FT_D = 0x5149;
constexpr int OFF_RES = 12 * UNIT;
constexpr int OFF_PAR = 14 * UNIT;
constexpr int OFF_BAR = OFF_PAR + 2528;
constexpr int SMEM_BYTES = OFF_BAR + 544;
static_assert(SMEM_BYTES <= 232448, "smem");

constexpr int PAR_T1 = 0;
constexpr int PAR_T2 = 512;
constexpr int PAR_CONST = 1536;
constexpr int PAR_RED = 1600;
constexpr int PAR_SINK = 2176;

struct Maps {
  CUtensorMap x, wq, k, v, wo, wg, wu, wd, wm, out;
};
struct Ptrs {
  const __nv_bfloat16 *x, *w_r, *c, *w_mod, *w_gate, *w_up, *w_down;
  __nv_bfloat16* out;
};

__device__ __align__(1024) uint8_t g_act[16 * 80 * UNIT];
__device__ __align__(128) uint32_t g_mod[NMOD];
__device__ __align__(128) uint32_t g_modp[2 * 2 * DM];
__device__ __align__(128) uint32_t g_ln1[SEQ * 4];
__device__ __align__(128) uint32_t g_cnt_h[16 * 32];
__device__ __align__(128) uint32_t g_cnt_o[128 * 32];
__device__ __align__(128) uint32_t g_xch[NMAIN * 8 * 256 * 4];
__device__ __align__(128) uint32_t g_stats[8 * SEQ * 4];
__device__ __align__(128) uint32_t g_cand[32];
__device__ __align__(128) uint32_t g_row[16 * 2 * DM];
__device__ __align__(128) uint32_t g_ypart[NMAIN * NFFN * 8];
__device__ uint32_t g_epoch;

__device__ __forceinline__ uint32_t fresh_lane() { uint32_t l; asm volatile("mov.u32 %0, %%laneid;" : "=r"(l)); return l; }
__device__ __forceinline__ uint32_t frag_offset(int warp) {
  const uint32_t l = fresh_lane();
  return ((warp & 3) * 16 + (l & 15)) * 128 + (((l >> 4) ^ (l & 7)) << 4);
}
__device__ __forceinline__ bool elect_one() {
  uint32_t p;
  asm volatile("{ .reg .pred q; elect.sync _|q, 0xffffffff; selp.u32 %0, 1, 0, q; }" : "=r"(p));
  return p;
}
__device__ __forceinline__ uint32_t smem_u32(const void* p) { return (uint32_t)__cvta_generic_to_shared(p); }
__device__ __forceinline__ void mbar_init(uint32_t bar, uint32_t cnt) {
  asm volatile("mbarrier.init.shared::cta.b64 [%0], %1;" ::"r"(bar), "r"(cnt) : "memory");
}
__device__ __forceinline__ void mbar_expect_tx(uint32_t bar, uint32_t bytes) {
  asm volatile("mbarrier.arrive.expect_tx.shared::cta.b64 _, [%0], %1;" ::"r"(bar), "r"(bytes) : "memory");
}
__device__ __forceinline__ void mbar_arrive(uint32_t bar) {
  asm volatile("mbarrier.arrive.shared::cta.b64 _, [%0];" ::"r"(bar) : "memory");
}
__device__ __forceinline__ void mbar_arrive_pred(uint32_t bar, bool p) {
  asm volatile("{ .reg .pred p; setp.ne.b32 p, %1, 0; @p mbarrier.arrive.shared::cta.b64 _, [%0]; }" ::"r"(bar), "r"((int)p) : "memory");
}
__device__ __forceinline__ void mbar_arrive_cl(uint32_t bar, uint32_t off, bool p = true) {
  asm volatile("{ .reg .pred p, q; .reg .b32 a; setp.ne.b32 q, %2, 0; setp.ne.and.b32 p, %0, 0, q; add.u32 a, %0, %1; @p mbarrier.arrive.shared::cluster.b64 _, [a]; }"
               ::"r"(bar), "r"(off), "r"((int)p) : "memory");
}
__device__ __forceinline__ uint32_t mapa(uint32_t addr, uint32_t cta) {
  uint32_t r; asm("mapa.shared::cluster.u32 %0, %1, %2;" : "=r"(r) : "r"(addr), "r"(cta)); return r;
}
__device__ __forceinline__ void cluster_arrive() { asm volatile("barrier.cluster.arrive.relaxed.aligned;" ::: "memory"); }
__device__ __forceinline__ void cluster_wait() { asm volatile("barrier.cluster.wait.aligned;" ::: "memory"); }
__device__ __forceinline__ void watchdog(uint32_t& n) {
}
__device__ __forceinline__ void mbar_wait(uint32_t bar, uint32_t parity) {
  asm volatile("{\n.reg .pred p;\nWAIT_%=:\nmbarrier.try_wait.parity.shared::cta.b64 p, [%0], %1;\n@!p bra WAIT_%=;\n}" ::"r"(bar), "r"(parity) : "memory");
}
__device__ __forceinline__ bool mbar_test(uint32_t bar, uint32_t parity) {
  uint32_t ok;
  asm volatile("{\n.reg .pred p;\nmbarrier.test_wait.parity.shared::cta.b64 p, [%1], %2;\nselp.u32 %0, 1, 0, p;\n}" : "=r"(ok) : "r"(bar), "r"(parity) : "memory");
  return ok;
}
__device__ __forceinline__ uint64_t l2_stream() {
  uint64_t f; asm("createpolicy.fractional.L2::evict_first.b64 %0, 1.0;" : "=l"(f)); return f;
}
__device__ __forceinline__ void tma2d(uint32_t dst, const CUtensorMap* m, int c0, int c1, uint32_t bar) {
  asm volatile("cp.async.bulk.tensor.2d.shared::cluster.global.mbarrier::complete_tx::bytes.L2::cache_hint [%0], [%1, {%3, %4}], [%2], %5;"
               ::"r"(dst), "l"(m), "r"(bar), "r"(c0), "r"(c1), "l"(l2_stream()) : "memory");
}
__device__ __forceinline__ void bulk_load(uint32_t dst, const void* src, uint32_t bytes, uint32_t bar) {
  asm volatile("cp.async.bulk.shared::cluster.global.mbarrier::complete_tx::bytes [%0], [%1], %2, [%3];" ::"r"(dst), "l"(src), "r"(bytes), "r"(bar) : "memory");
}
__device__ __forceinline__ void bulk_load_stream(uint32_t dst, const void* src, uint32_t bytes, uint32_t bar) {
  asm volatile("cp.async.bulk.shared::cluster.global.mbarrier::complete_tx::bytes.L2::cache_hint [%0], [%1], %2, [%3], %4;"
               ::"r"(dst), "l"(src), "r"(bytes), "r"(bar), "l"(l2_stream()) : "memory");
}
__device__ __forceinline__ void tma2d_store(const CUtensorMap* m, uint32_t src, int c0, int c1) {
  asm volatile("cp.async.bulk.tensor.2d.global.shared::cta.bulk_group [%0, {%2, %3}], [%1];" ::"l"(m), "r"(src), "r"(c0), "r"(c1) : "memory");
}
__device__ __forceinline__ void bulk_store(void* dst, uint32_t src, uint32_t bytes) {
  asm volatile("cp.async.bulk.global.shared::cta.bulk_group [%0], [%1], %2;" ::"l"(dst), "r"(src), "r"(bytes) : "memory");
}
__device__ __forceinline__ uint32_t unit_of(uint32_t table, uint32_t i) { return ((table >> (i * 4)) & 15) * UNIT; }
__device__ __forceinline__ void tma3d(uint32_t dst, const CUtensorMap* m, int c0, int c1, int c2, uint32_t bar) {
  asm volatile("cp.async.bulk.tensor.3d.shared::cluster.global.mbarrier::complete_tx::bytes.L2::cache_hint [%0], [%1, {%3, %4, %5}], [%2], %6;"
               ::"r"(dst), "l"(m), "r"(bar), "r"(c0), "r"(c1), "r"(c2), "l"(l2_stream()) : "memory");
}
template <bool STREAM>
__device__ __forceinline__ void tma3d_mc(uint32_t dst, const CUtensorMap* m, int c0, int c1, int c2, uint32_t bar) {
  if (STREAM)
    asm volatile("cp.async.bulk.tensor.3d.shared::cluster.global.mbarrier::complete_tx::bytes.multicast::cluster.L2::cache_hint [%0], [%1, {%3, %4, %5}], [%2], %6, %7;"
                 ::"r"(dst), "l"(m), "r"(bar), "r"(c0), "r"(c1), "r"(c2), "h"((uint16_t)3), "l"(l2_stream()) : "memory");
  else
    asm volatile("cp.async.bulk.tensor.3d.shared::cluster.global.mbarrier::complete_tx::bytes.multicast::cluster [%0], [%1, {%3, %4, %5}], [%2], %6;"
                 ::"r"(dst), "l"(m), "r"(bar), "r"(c0), "r"(c1), "r"(c2), "h"((uint16_t)3) : "memory");
}
__device__ __forceinline__ void prefetch_map(const CUtensorMap* m) {
  asm volatile("prefetch.tensormap [%0];" ::"l"(m) : "memory");
}
__device__ __forceinline__ void fence_async() { asm volatile("fence.proxy.async.global;" ::: "memory"); }
__device__ __forceinline__ void fence_async_smem() { asm volatile("fence.proxy.async.shared::cta;" ::: "memory"); }
__device__ __forceinline__ void bar_sync(int id, int n) { asm volatile("bar.sync %0, %1;" ::"r"(id), "r"(n) : "memory"); }
__device__ __forceinline__ void bar_arrive(int id, int n) { asm volatile("bar.arrive %0, %1;" ::"r"(id), "r"(n) : "memory"); }
__device__ __forceinline__ void wg_fence() { asm volatile("wgmma.fence.sync.aligned;" ::: "memory"); }
__device__ __forceinline__ void wg_commit() { asm volatile("wgmma.commit_group.sync.aligned;" ::: "memory"); }
template <int N> __device__ __forceinline__ void wg_wait() { asm volatile("wgmma.wait_group.sync.aligned %0;" ::"n"(N) : "memory"); }
__device__ __forceinline__ uint64_t make_desc(uint32_t addr, uint32_t lbo, uint32_t sbo) {
  return (uint64_t)((addr & 0x3FFFF) >> 4) | ((uint64_t)(lbo >> 4) << 16) | ((uint64_t)(sbo >> 4) << 32) | (1ull << 62);
}
__device__ __forceinline__ uint32_t ld_relaxed(const uint32_t* p) {
  uint32_t v; asm volatile("ld.relaxed.gpu.global.u32 %0, [%1];" : "=r"(v) : "l"(p) : "memory"); return v;
}
__device__ __forceinline__ uint32_t ld_acquire(const uint32_t* p) {
  uint32_t v; asm volatile("ld.acquire.gpu.global.u32 %0, [%1];" : "=r"(v) : "l"(p) : "memory"); return v;
}
__device__ __forceinline__ uint4 ld_relaxed4(const uint32_t* p) {
  uint4 v; asm volatile("ld.relaxed.gpu.global.v4.u32 {%0,%1,%2,%3}, [%4];" : "=r"(v.x), "=r"(v.y), "=r"(v.z), "=r"(v.w) : "l"(p) : "memory"); return v;
}
__device__ __forceinline__ uint2 ld_relaxed2(const uint32_t* p) {
  uint2 v; asm volatile("ld.relaxed.gpu.global.v2.u32 {%0,%1}, [%2];" : "=r"(v.x), "=r"(v.y) : "l"(p) : "memory"); return v;
}
__device__ __forceinline__ void st_relaxed(uint32_t* p, uint32_t v) {
  asm volatile("st.relaxed.gpu.global.u32 [%0], %1;" ::"l"(p), "r"(v) : "memory");
}
__device__ __forceinline__ void st_relaxed2(uint32_t* p, uint32_t a, uint32_t b) {
  asm volatile("st.relaxed.gpu.global.v2.u32 [%0], {%1,%2};" ::"l"(p), "r"(a), "r"(b) : "memory");
}
__device__ __forceinline__ void st_relaxed4(uint32_t* p, uint32_t a, uint32_t b, uint32_t c, uint32_t d) {
  asm volatile("st.relaxed.gpu.global.v4.u32 [%0], {%1,%2,%3,%4};" ::"l"(p), "r"(a), "r"(b), "r"(c), "r"(d) : "memory");
}
__device__ __forceinline__ void st_b128(uint32_t* p, uint32_t a, uint32_t b, uint32_t c, uint32_t d) {
  asm volatile("{ .reg .b64 u, v; .reg .b128 w; mov.b64 u, {%1, %2}; mov.b64 v, {%3, %4}; mov.b128 w, {u, v}; st.relaxed.gpu.global.b128 [%0], w; }"
               ::"l"(p), "r"(a), "r"(b), "r"(c), "r"(d) : "memory");
}
__device__ __forceinline__ uint4 ld_b128(const uint32_t* p) {
  uint4 r;
  asm volatile("{ .reg .b64 u, v; .reg .b128 w; ld.relaxed.gpu.global.b128 w, [%4]; mov.b128 {u, v}, w; mov.b64 {%0, %1}, u; mov.b64 {%2, %3}, v; }"
               : "=r"(r.x), "=r"(r.y), "=r"(r.z), "=r"(r.w) : "l"(p) : "memory");
  return r;
}
__device__ __forceinline__ void st_pairs(uint32_t* p, uint32_t a, uint32_t b, uint32_t tag) {
  asm volatile("{ .reg .b64 u, v; mov.b64 u, {%1, %3}; mov.b64 v, {%2, %3}; st.relaxed.gpu.global.v2.b64 [%0], {u, v}; }"
               ::"l"(p), "r"(a), "r"(b), "r"(tag) : "memory");
}
__device__ __forceinline__ uint4 ld_pairs(const uint32_t* p) {
  uint4 v;
  asm volatile("{ .reg .b64 u, v; ld.relaxed.gpu.global.v2.b64 {u, v}, [%4]; mov.b64 {%0, %1}, u; mov.b64 {%2, %3}, v; }"
               : "=r"(v.x), "=r"(v.y), "=r"(v.z), "=r"(v.w) : "l"(p) : "memory");
  return v;
}
__device__ __forceinline__ uint2 ld_pair(const uint32_t* p) {
  uint2 v;
  asm volatile("{ .reg .b64 u; ld.relaxed.gpu.global.b64 u, [%2]; mov.b64 {%0, %1}, u; }" : "=r"(v.x), "=r"(v.y) : "l"(p) : "memory");
  return v;
}
__device__ __forceinline__ void red_release(uint32_t* p, uint32_t v) {
  asm volatile("red.release.gpu.global.add.u32 [%0], %1;" ::"l"(p), "r"(v) : "memory");
}
__device__ __forceinline__ uint32_t ldg_nc1(const void* p) {
  uint32_t v;
  asm volatile("ld.global.nc.u32 %0, [%1];" : "=r"(v) : "l"(p));
  return v;
}
__device__ __forceinline__ uint4 ldg_nc4(const void* p) {
  uint4 v; asm volatile("ld.global.nc.L1::no_allocate.v4.u32 {%0,%1,%2,%3}, [%4];" : "=r"(v.x), "=r"(v.y), "=r"(v.z), "=r"(v.w) : "l"(p)); return v;
}
__device__ __forceinline__ uint4 ldg_stream4(const void* p) {
  uint4 v;
  asm volatile("ld.global.nc.L1::no_allocate.L2::cache_hint.v4.u32 {%0,%1,%2,%3}, [%4], %5;" : "=r"(v.x), "=r"(v.y), "=r"(v.z), "=r"(v.w) : "l"(p), "l"(l2_stream()));
  return v;
}
__device__ __forceinline__ void stg4(void* p, uint4 v) {
  asm volatile("st.global.v4.u32 [%0], {%1,%2,%3,%4};" ::"l"(p), "r"(v.x), "r"(v.y), "r"(v.z), "r"(v.w) : "memory");
}
__device__ __forceinline__ void wait_counter(const uint32_t* p, uint32_t target) {
  uint32_t n = 0;
  while (__any_sync(0xffffffffu, (int)(ld_acquire(p) - target) < 0)) { watchdog(n); }
}
__device__ __forceinline__ uint32_t tagf(float v, uint32_t tag) { return (__float_as_uint(v) & ~3u) | tag; }
__device__ __forceinline__ bool tag_ok(uint4 v, uint32_t tag) { return (((v.x ^ tag) | (v.y ^ tag) | (v.z ^ tag) | (v.w ^ tag)) & 3u) == 0; }
__device__ __forceinline__ float untag_sum(uint32_t a, uint32_t b) { return __uint_as_float(a & ~3u) + __uint_as_float(b & ~3u); }
__device__ __forceinline__ uint4 poll4(const uint32_t* p, uint32_t tag) {
  uint4 v = ld_relaxed4(p);
  uint32_t n = 0;
  while (!__all_sync(0xffffffffu, tag_ok(v, tag))) { v = ld_relaxed4(p); watchdog(n); }
  return v;
}
__device__ __forceinline__ float bf_lo(uint32_t v) { return __uint_as_float(v << 16); }
__device__ __forceinline__ float bf_hi(uint32_t v) { return __uint_as_float(v & 0xffff0000u); }
__device__ __forceinline__ uint32_t pack_bf(float lo, float hi) {
  uint32_t r; asm("cvt.rn.bf16x2.f32 %0, %1, %2;" : "=r"(r) : "f"(hi), "f"(lo)); return r;
}
__device__ __forceinline__ float rbf(float v) { return __uint_as_float(pack_bf(0.f, v) & 0xffff0000u); }
__device__ __forceinline__ uint32_t hmul2(uint32_t a, uint32_t b) {
  uint32_t r; asm("mul.rn.bf16x2 %0, %1, %2;" : "=r"(r) : "r"(a), "r"(b)); return r;
}
__device__ __forceinline__ uint32_t hadd2(uint32_t a, uint32_t b) {
  uint32_t r; asm("add.rn.bf16x2 %0, %1, %2;" : "=r"(r) : "r"(a), "r"(b)); return r;
}
__device__ __forceinline__ uint32_t hsub2(uint32_t a, uint32_t b) {
  uint32_t r; asm("sub.rn.bf16x2 %0, %1, %2;" : "=r"(r) : "r"(a), "r"(b)); return r;
}
__device__ __forceinline__ uint32_t hmax2(uint32_t a, uint32_t b) {
  uint32_t r; asm("max.bf16x2 %0, %1, %2;" : "=r"(r) : "r"(a), "r"(b)); return r;
}
__device__ __forceinline__ float rcp(float x) { float r; asm("rcp.approx.ftz.f32 %0, %1;" : "=f"(r) : "f"(x)); return r; }
__device__ __forceinline__ float ex2(float x) { float r; asm("ex2.approx.ftz.f32 %0, %1;" : "=f"(r) : "f"(x)); return r; }
__device__ __forceinline__ void stmatrix4(uint32_t addr, uint32_t a, uint32_t b, uint32_t c, uint32_t d) {
  asm volatile("stmatrix.sync.aligned.m8n8.x4.shared.b16 [%0], {%1,%2,%3,%4};" ::"r"(addr), "r"(a), "r"(b), "r"(c), "r"(d) : "memory");
}
__device__ __forceinline__ void ldmatrix4(uint32_t addr, uint32_t& a, uint32_t& b, uint32_t& c, uint32_t& d) {
  asm volatile("ldmatrix.sync.aligned.m8n8.x4.shared.b16 {%0,%1,%2,%3}, [%4];" : "=r"(a), "=r"(b), "=r"(c), "=r"(d) : "r"(addr) : "memory");
}
__device__ __forceinline__ void ldmatrix4t(uint32_t addr, uint32_t& a, uint32_t& b, uint32_t& c, uint32_t& d) {
  asm volatile("ldmatrix.sync.aligned.m8n8.x4.trans.shared.b16 {%0,%1,%2,%3}, [%4];" : "=r"(a), "=r"(b), "=r"(c), "=r"(d) : "r"(addr) : "memory");
}
__device__ __forceinline__ void mma16816(float (&d)[4], uint32_t a0, uint32_t a1, uint32_t a2, uint32_t a3, uint32_t b0, uint32_t b1) {
  asm volatile("mma.sync.aligned.m16n8k16.row.col.f32.bf16.bf16.f32 {%0,%1,%2,%3}, {%4,%5,%6,%7}, {%8,%9}, {%0,%1,%2,%3};"
               : "+f"(d[0]), "+f"(d[1]), "+f"(d[2]), "+f"(d[3]) : "r"(a0), "r"(a1), "r"(a2), "r"(a3), "r"(b0), "r"(b1));
}
__device__ __forceinline__ void sts1(uint32_t a, uint32_t v) { asm volatile("st.shared.u32 [%0], %1;" ::"r"(a), "r"(v) : "memory"); }
__device__ __forceinline__ uint4 lds4(uint32_t a) {
  uint4 v; asm volatile("ld.shared.v4.u32 {%0,%1,%2,%3}, [%4];" : "=r"(v.x), "=r"(v.y), "=r"(v.z), "=r"(v.w) : "r"(a) : "memory"); return v;
}
__device__ __forceinline__ uint2 lds2(uint32_t a) {
  uint2 v; asm volatile("ld.shared.v2.u32 {%0,%1}, [%2];" : "=r"(v.x), "=r"(v.y) : "r"(a) : "memory"); return v;
}
__device__ __forceinline__ uint32_t lds1(uint32_t a) {
  uint32_t v; asm volatile("ld.shared.u32 %0, [%1];" : "=r"(v) : "r"(a) : "memory"); return v;
}
__device__ __forceinline__ void sts2(uint32_t a, uint32_t x, uint32_t y) { asm volatile("st.shared.v2.u32 [%0], {%1,%2};" ::"r"(a), "r"(x), "r"(y) : "memory"); }
__device__ __forceinline__ void sts4(uint32_t a, uint4 v) {
  asm volatile("st.shared.v4.u32 [%0], {%1,%2,%3,%4};" ::"r"(a), "r"(v.x), "r"(v.y), "r"(v.z), "r"(v.w) : "memory");
}
__device__ __forceinline__ float silu_f(float v) { return __fdividef(v, 1.f + __expf(-v)); }
__device__ __forceinline__ uint32_t hfma2(uint32_t a, uint32_t b, uint32_t c) {
  uint32_t r; asm("fma.rn.bf16x2 %0, %1, %2, %3;" : "=r"(r) : "r"(a), "r"(b), "r"(c)); return r;
}
__device__ __forceinline__ void split_inv(float sd, uint32_t& ih, uint32_t& il) {
  const float inv = rcp(sd);
  ih = pack_bf(inv, inv);
  const float lo = inv - bf_lo(ih);
  il = pack_bf(lo, lo);
}
__device__ __forceinline__ uint32_t ln_norm(uint32_t x, uint32_t mean2, uint32_t ih, uint32_t il) {
  const uint32_t d = hsub2(x, mean2);
  return hfma2(d, ih, hmul2(d, il));
}
__device__ __forceinline__ uint32_t modul(uint32_t n, uint32_t c1, uint32_t sh) { return hadd2(hmul2(n, c1), sh); }
__device__ __forceinline__ uint32_t ln_mod(uint32_t x, uint32_t mean2, uint32_t ih, uint32_t il, uint32_t c1, uint32_t sh) {
  return modul(ln_norm(x, mean2, ih, il), c1, sh);
}

#define R8(a, i) "+f"(a[i]), "+f"(a[i + 1]), "+f"(a[i + 2]), "+f"(a[i + 3]), "+f"(a[i + 4]), "+f"(a[i + 5]), "+f"(a[i + 6]), "+f"(a[i + 7])
#define D64 "{%0,%1,%2,%3,%4,%5,%6,%7,%8,%9,%10,%11,%12,%13,%14,%15,%16,%17,%18,%19,%20,%21,%22,%23,%24,%25,%26,%27,%28,%29,%30,%31," \
            "%32,%33,%34,%35,%36,%37,%38,%39,%40,%41,%42,%43,%44,%45,%46,%47,%48,%49,%50,%51,%52,%53,%54,%55,%56,%57,%58,%59,%60,%61,%62,%63}"
template <int TB>
__device__ __forceinline__ void mma_ss(float (&d)[64], uint64_t da, uint64_t db, int sc) {
  asm volatile("{\n.reg .pred p;\nsetp.ne.b32 p, %66, 0;\n"
               "wgmma.mma_async.sync.aligned.m64n128k16.f32.bf16.bf16 " D64 ", %64, %65, p, 1, 1, 0, %67;\n}"
               : R8(d, 0), R8(d, 8), R8(d, 16), R8(d, 24), R8(d, 32), R8(d, 40), R8(d, 48), R8(d, 56)
               : "l"(da), "l"(db), "r"(sc), "n"(TB));
}
template <int TB>
__device__ __forceinline__ void mma_rs(float (&d)[64], uint32_t a0, uint32_t a1, uint32_t a2, uint32_t a3, uint64_t db, int sc) {
  asm volatile("{\n.reg .pred p;\nsetp.ne.b32 p, %69, 0;\n"
               "wgmma.mma_async.sync.aligned.m64n128k16.f32.bf16.bf16 " D64 ", {%64,%65,%66,%67}, %68, p, 1, 1, %70;\n}"
               : R8(d, 0), R8(d, 8), R8(d, 16), R8(d, 24), R8(d, 32), R8(d, 40), R8(d, 48), R8(d, 56)
               : "r"(a0), "r"(a1), "r"(a2), "r"(a3), "l"(db), "r"(sc), "n"(TB));
}
#define D128 "{%0,%1,%2,%3,%4,%5,%6,%7,%8,%9,%10,%11,%12,%13,%14,%15,%16,%17,%18,%19,%20,%21,%22,%23,%24,%25,%26,%27,%28,%29,%30,%31," \
             "%32,%33,%34,%35,%36,%37,%38,%39,%40,%41,%42,%43,%44,%45,%46,%47,%48,%49,%50,%51,%52,%53,%54,%55,%56,%57,%58,%59,%60,%61,%62,%63," \
             "%64,%65,%66,%67,%68,%69,%70,%71,%72,%73,%74,%75,%76,%77,%78,%79,%80,%81,%82,%83,%84,%85,%86,%87,%88,%89,%90,%91,%92,%93,%94,%95," \
             "%96,%97,%98,%99,%100,%101,%102,%103,%104,%105,%106,%107,%108,%109,%110,%111,%112,%113,%114,%115,%116,%117,%118,%119,%120,%121,%122,%123,%124,%125,%126,%127}"
#define R128(d, e) R8(d, 0), R8(d, 8), R8(d, 16), R8(d, 24), R8(d, 32), R8(d, 40), R8(d, 48), R8(d, 56), \
                   R8(e, 0), R8(e, 8), R8(e, 16), R8(e, 24), R8(e, 32), R8(e, 40), R8(e, 48), R8(e, 56)
__device__ __forceinline__ void mma256_ss(float (&d)[64], float (&e)[64], uint64_t da, uint64_t db, int sc) {
  asm volatile("{\n.reg .pred p;\nsetp.ne.b32 p, %130, 0;\n"
               "wgmma.mma_async.sync.aligned.m64n256k16.f32.bf16.bf16 " D128 ", %128, %129, p, 1, 1, 0, 1;\n}"
               : R128(d, e) : "l"(da), "l"(db), "r"(sc));
}
__device__ __forceinline__ void mma256_rs(float (&d)[64], float (&e)[64], uint32_t a0, uint32_t a1, uint32_t a2, uint32_t a3, uint64_t db) {
  asm volatile("{\n.reg .pred p;\nsetp.ne.b32 p, 1, 0;\n"
               "wgmma.mma_async.sync.aligned.m64n256k16.f32.bf16.bf16 " D128 ", {%128,%129,%130,%131}, %132, p, 1, 1, 1;\n}"
               : R128(d, e) : "r"(a0), "r"(a1), "r"(a2), "r"(a3), "l"(db));
}
template <int N> __device__ __forceinline__ void keep(float (&a)[N]) {
#pragma unroll
  for (int i = 0; i < N; i++) asm volatile("" : "+f"(a[i])::"memory");
}
template <int N> __device__ __forceinline__ void keep(uint32_t (&a)[N]) {
#pragma unroll
  for (int i = 0; i < N; i++) asm volatile("" : "+r"(a[i])::"memory");
}

#define STAMP(idx) do {} while (0)
#define PROF(grp, cond, idx) do {} while (0)

constexpr float SCL2 = 1.4426950408889634f * 0.08838834764831845f;

__device__ __forceinline__ void pack_p(const float (&s)[64], uint32_t (&p)[32]) {
#pragma unroll
  for (int i = 0; i < 32; i++) p[i] = pack_bf(s[2 * i], s[2 * i + 1]);
}

__device__ __forceinline__ void issue_qk(float (&s)[64], uint32_t q0, uint32_t q1, uint32_t kslot) {
  const uint64_t db = make_desc(kslot, 16, 1024), da0 = make_desc(q0, 16, 1024), da1 = make_desc(q1, 16, 1024);
#pragma unroll
  for (int kk = 0; kk < 8; kk++) mma_ss<0>(s, (kk < 4 ? da0 : da1) + (kk & 3) * 2, db + (kk >> 2) * 1024 + (kk & 3) * 2, kk != 0);
}
__device__ __forceinline__ void issue_pv(float (&o)[64], uint32_t (&p)[32], uint32_t vslot, int acc) {
  uint64_t db = make_desc(vslot, 16384, 1024);
#pragma unroll
  for (int kk = 0; kk < 8; kk++)
    mma_rs<1>(o, p[4 * kk], p[4 * kk + 1], p[4 * kk + 2], p[4 * kk + 3], db + kk * 128, kk == 0 ? acc : 1);
}

template <int H>
__device__ __forceinline__ void store_chunk(const float (&a)[64], uint32_t addr) {
#pragma unroll
  for (int i = 8 * H; i < 8 * H + 8; i += 2)
    stmatrix4(addr ^ ((i & 7) << 4), pack_bf(a[4 * i], a[4 * i + 1]), pack_bf(a[4 * i + 2], a[4 * i + 3]),
              pack_bf(a[4 * i + 4], a[4 * i + 5]), pack_bf(a[4 * i + 6], a[4 * i + 7]));
}
template <int H>
__device__ __forceinline__ void store_chunk(const float (&a)[64], float i0, float i1, uint32_t addr) {
#pragma unroll
  for (int i = 8 * H; i < 8 * H + 8; i += 2)
    stmatrix4(addr ^ ((i & 7) << 4), pack_bf(a[4 * i] * i0, a[4 * i + 1] * i0), pack_bf(a[4 * i + 2] * i1, a[4 * i + 3] * i1),
              pack_bf(a[4 * i + 4] * i0, a[4 * i + 5] * i0), pack_bf(a[4 * i + 6] * i1, a[4 * i + 7] * i1));
}
__device__ __forceinline__ float inv_quad_sum(float l) {
  l += __shfl_xor_sync(0xffffffffu, l, 1);
  l += __shfl_xor_sync(0xffffffffu, l, 2);
  return rcp(l);
}

__device__ __forceinline__ void ln_scalars(float mean, float var, float& mb, float& sd) {
  mb = rbf(mean);
  float r; asm("sqrt.approx.ftz.f32 %0, %1;" : "=f"(r) : "f"(rbf(rbf(var) + 1e-5f)));
  sd = rbf(r);
}

__global__ void __cluster_dims__(2, 1, 1) __launch_bounds__(384, 1) fused_kernel(const __grid_constant__ Maps maps, const Ptrs P) {
  extern __shared__ __align__(1024) uint8_t smem_raw[];
  const uint32_t base = smem_u32(smem_raw);
  const int tid = threadIdx.x, lane = tid & 31;
  const int warp = __shfl_sync(0xffffffffu, tid >> 5, 0);
  const int b = blockIdx.x;
  PROF(31, tid == 0, 0);

  if (b >= NMAIN) {
    float* sc = reinterpret_cast<float*>(smem_raw);
    float* red = sc + DM;
    for (int k = tid; k < DM; k += 384) sc[k] = rbf(silu_f(__bfloat162float(P.c[k])));
    __syncthreads();
    if (tid < 256) {
      const int col = 2048 + (b - NMAIN) * 1024 + (tid & 127) * 8, r0 = (tid >> 7) * 512;
      float acc[8];
#pragma unroll
      for (int e = 0; e < 8; e++) acc[e] = 0.f;
#pragma unroll 1
      for (int r = r0; r < r0 + 512; r += HU) {
        uint4 w[HU];
#pragma unroll
        for (int u = 0; u < HU; u++) w[u] = ldg_stream4(P.w_mod + (size_t)(r + u) * NMOD + col);
#pragma unroll
        for (int u = 0; u < HU; u++) {
          float s = sc[r + u];
          acc[0] += s * bf_lo(w[u].x); acc[1] += s * bf_hi(w[u].x); acc[2] += s * bf_lo(w[u].y); acc[3] += s * bf_hi(w[u].y);
          acc[4] += s * bf_lo(w[u].z); acc[5] += s * bf_hi(w[u].z); acc[6] += s * bf_lo(w[u].w); acc[7] += s * bf_hi(w[u].w);
        }
      }
      if (tid >= 128) {
#pragma unroll
        for (int e = 0; e < 8; e++) red[(tid & 127) * 8 + e] = acc[e];
      }
      const uint32_t tag = ld_relaxed(&g_epoch) % 3 + 1;
      bar_sync(1, 256);
      if (tid < 128) {
        uint32_t o[8];
#pragma unroll
        for (int e = 0; e < 8; e++) o[e] = __float_as_uint(rbf(acc[e] + red[tid * 8 + e])) | tag;
        st_relaxed4(g_mod + col, o[0], o[1], o[2], o[3]);
        st_relaxed4(g_mod + col + 4, o[4], o[5], o[6], o[7]);
        const uint4 wr = ldg_nc4(P.w_r + tid * 8);
        const uint32_t wv[4] = {wr.x, wr.y, wr.z, wr.w};
        float dsum = 0.f;
#pragma unroll
        for (int e = 0; e < 8; e++) {
          const float m = bf_hi(o[e]);
          dsum += (b == NMAIN + 2 ? rbf(1.f + m) : m) * ((e & 1) ? bf_hi(wv[e >> 1]) : bf_lo(wv[e >> 1]));
        }
#pragma unroll
        for (int k = 16; k > 0; k >>= 1) dsum += __shfl_xor_sync(0xffffffffu, dsum, k);
        if (lane == 0) st_relaxed(g_mod + (b - NMAIN) * 4 + warp, tagf(dsum, tag));
      }
    }
    PROF(2, tid == 0, 1);
    return;
  }

  const int rank = b & 1;
  const int rb = ((b >> 4) << 1) | rank, cj = (b >> 1) & 7;
  const uint32_t bfull = base + OFF_BAR, bempty = bfull + NSLOT * 8;
  const uint32_t gfull = bempty + NSLOT * 8, gempty = gfull + 32;
  const uint32_t bar_ofull = gempty + 32;
  const uint32_t bar_ofree = bar_ofull + 32;
  const uint32_t bar_par = bar_ofree + 32;
  const uint32_t bar_mod = bar_par + 8;
  const uint32_t bar_pread = bar_mod + 8;
  const uint32_t bar_xres = bar_pread + 8;
  const uint32_t bar_ring = bar_xres + 8;
  const uint32_t bar_box = bar_ring + 24;
  const uint32_t bar_go = bar_box + 96;
  const uint32_t bar_go2 = bar_go + 16;
  const uint32_t bar_cnt = bar_go + 24;
  const uint32_t xfull = bar_go + 32, xempty = xfull + 32;
  const uint32_t bar_hw = xempty + 32, bar_hx = bar_hw + 8;
  const uint32_t bar_hpub = bar_hx + 16;
  const uint32_t bar_win = bar_hpub + 16;
  const uint32_t bar_rx = bar_win + 8;
  const uint32_t bar_sel = bar_rx + 8;
  const uint32_t bar_gate = bar_sel + 8;
  const uint32_t bar_rel = bar_gate + 8;
  const uint32_t bar_od = bar_rel + 8;
  const uint32_t bar_res = bar_go + 8;
  const uint32_t stage = base + OFF_STAGE, par = base + OFF_PAR;

  if (warp == 8 && elect_one()) {
    for (int s = 0; s < NSLOT; s++) { mbar_init(bfull + s * 8, 1); mbar_init(bempty + s * 8, 16); }
    for (int s = 0; s < 4; s++) { mbar_init(gfull + s * 8, 1); mbar_init(gempty + s * 8, 16); mbar_init(xfull + s * 8, 1); mbar_init(xempty + s * 8, 8); mbar_init(bar_ofree + s * 8, 1); mbar_init(bar_ofull + s * 8, 128); }
    mbar_init(bar_par, 64); mbar_init(bar_mod, 256); mbar_init(bar_pread, 2); mbar_init(bar_xres, 1);
    mbar_init(bar_ring, 8); mbar_init(bar_ring + 8, 8); mbar_init(bar_ring + 16, 8);
    mbar_init(bar_go, 1); mbar_init(bar_go2, 1); mbar_init(bar_cnt, 1); mbar_init(bar_hpub, 8); mbar_init(bar_hpub + 8, 8); mbar_init(bar_res, 1); mbar_init(bar_win, 1); mbar_init(bar_rx, 1); mbar_init(bar_sel, 64); mbar_init(bar_gate, 8); mbar_init(bar_rel, 8); mbar_init(bar_od, 1);
    for (int s = 0; s < 12; s++) mbar_init(bar_box + s * 8, 1);
    asm volatile("fence.mbarrier_init.release.cluster;" ::: "memory");
    prefetch_map(&maps.x); prefetch_map(&maps.wq); prefetch_map(&maps.k); prefetch_map(&maps.v);
  }
  if (warp == 9 && elect_one()) {
    mbar_init(bar_hw, 1); mbar_init(bar_hx, 1); mbar_init(bar_hx + 8, 1);
    asm volatile("fence.mbarrier_init.release.cluster;" ::: "memory");
    mbar_expect_tx(bar_hw, 32768);
    mbar_expect_tx(bar_hx, 16384);
    mbar_expect_tx(bar_hx + 8, 16384);
    const __nv_bfloat16* xs = P.x + (size_t)(rb * 128 + cj * 16) * DM;
    bulk_load(base + 2 * GST_BYTES, xs, 16384, bar_hx);
    tma2d(stage, &maps.wm, (b >> 1) * 32, rank * 512, bar_hw);
    tma2d(stage + 16384, &maps.wm, (b >> 1) * 32, rank * 512 + 256, bar_hw);
    bulk_load(base + 3 * GST_BYTES, xs + 8 * DM, 16384, bar_hx + 8);
  }
  cluster_arrive();

  if (warp >= 8) {
    asm volatile("setmaxnreg.dec.sync.aligned.u32 40;");
    if (warp < 10) bar_arrive(1, 320);
    const uint32_t epoch = ld_relaxed(&g_epoch);
    cluster_wait();
    if (warp == 8) {
      const int kvrow = (cj >> 1) * SK + (SK - WIN);
      int wch = cj * 8 + rank * 2;
#pragma unroll 1
      for (int ps = 0; ps < 3; ps++) {
        const CUtensorMap* mw = ps == 2 ? &maps.wo : &maps.wq;
        const uint32_t xt = ps == 1 ? XT1 : XT2, wt = ps == 0 ? WT0 : (ps == 1 ? WT1 : WT2);
        const int nst = ps == 2 ? 32 : 16;
#pragma unroll 1
        for (int i = 0; i < nst; i++) {
          const uint32_t bf = gfull + (i & 3) * 8;
          const int kt = ps == 2 ? (((cj & 1) * 4 + ((i >> 1) & 3)) * 4 + (i >> 3)) * 2 + (i & 1) : (i + (ps ? 0 : b & 14)) & 15;
          const uint32_t wd = base + unit_of(wt, i & 3) + rank * UNIT, xd = base + unit_of(xt, i & 3);
          const uint8_t* xs = g_act + (uint32_t)(rb * 80 + (ps - 1) * 16 + kt) * UNIT;
          if (ps == 0 && i == HD) mbar_wait(bar_mod, 0);
          const bool xfirst = ps && i < 2;
          if (ps == 2 && i == 0) mbar_wait(bar_ofree + 24, 0);
          if (i == 0) fence_async();
          mbar_wait(gempty + (i & 3) * 8, ((i >> 2) & 1) ^ 1);
          if (elect_one()) {
            mbar_expect_tx(bf, ps ? GST_BYTES : 2 * UNIT);
            if (xfirst) bulk_load_stream(xd, xs, UNIT, bf);
          }
          if (ps && i < 4) mbar_wait(bempty + i * 8, 1);
          if (elect_one()) tma3d_mc<true>(wd, mw, 0, (i == 31 ? kt ^ (rank * 32) : kt) * 64, i == 31 ? cj * 2 : wch, bf);
          if (ps) {
            if (i == 16) { mbar_wait(bar_cnt, 0); fence_async(); }
            if (i == 2) mbar_wait(bar_ofree + (ps - 1) * 16, 0);
            if (elect_one()) {
              if (i == 31) bulk_load(xd, xs, UNIT, bf); else if (!xfirst) bulk_load_stream(xd, xs, UNIT, bf);
              mbar_arrive_pred(bar_go, i == GOST - 1);
              mbar_arrive_pred(bar_od, i == ODS);
              mbar_arrive_pred(bar_res, ((1u << RES0 | 1u << RES1) >> i) & 1);
            }
          }
        }
        if (ps == 2) break;
        wch = ps ? ((wch >> 3) ^ rank) * 2 : wch + 4;
#pragma unroll 1
        for (int u = 0; u < 16; u++) {
          const bool isk = (u == 0) || ((u & 1) && u < 15);
          const int blk = (isk ? (u + 1) >> 1 : (u == 15 ? 7 : (u >> 1) - 1)) & 3;
          const uint32_t sl = base + unit_of(ps ? AT1 : AT0, u & 3) + rank * UNIT, bf = bfull + (u & 3) * 8;
          if (u < 4) mbar_wait(gempty + ((u + 1) >> 1) * 8, 1);
          mbar_wait(bempty + (u & 3) * 8, ((u >> 2) & 1) ^ 1);
          if (elect_one()) {
            mbar_arrive_pred(bar_go2, ps && u == PG0);
            mbar_expect_tx(bf, SLOT_BYTES);
            tma3d_mc<false>(sl, isk ? &maps.k : &maps.v, 0, kvrow + blk * 128, rank, bf);
          }
        }
      }
      if (elect_one()) mbar_expect_tx(bar_rx, UNIT);
      mbar_wait(bar_rel, 0);
      if (elect_one()) {
        bulk_load_stream(base + UNIT, g_act + (uint32_t)(rb * 80 + 16 + 63 - (cj & 1) * 32) * UNIT, UNIT, bar_rx);
      }
      if (b < NFFN) {
#pragma unroll 1
        for (int u = 0; u < 12; u++) {
          const uint32_t dst = base + unit_of(u < 4 ? FT_G : (u < 8 ? FT_U : FT_D), u & 3);
          if (elect_one()) mbar_expect_tx(bar_box + u * 8, UNIT);
          if (u == FB0 || u == 2 || u == FB2) mbar_wait(bar_ring + (u == FB2 ? 16 : (u + 6) & 8), 0);
          if (u >= FPACE) mbar_wait(bar_box + (u - FPACE) * 8, 0);
          if (elect_one()) {
            if (u < 8) tma2d(dst, u < 4 ? &maps.wg : &maps.wu, b * 32, (u & 3) * 256, bar_box + u * 8);
            else tma3d(dst, &maps.wd, 0, b * 32, (u - 8) * 4, bar_box + u * 8);
          }
        }
      }
    } else if (warp == 9) {
      const uint32_t target = 8 * (epoch + 1);
      uint32_t hmask = 0;
#pragma unroll 1
      for (int i = 0; i < 16; i++) {
        if (i == HDX) mbar_wait(bar_mod, 0);
        const uint32_t need = i == 15 ? 0xffffu : 1u << ((2 * cj + i) & 15);
        if (i >= NRS && (hmask & need) != need) {
          uint32_t n = 0;
          do { hmask = __ballot_sync(0xffffffffu, ld_acquire(&g_cnt_h[rb * 32 + (lane & 15)]) == HCP * (epoch + 1)); watchdog(n); } while ((hmask & need) != need);
          PROF(1, lane == 0 && i == NRS, 26);
          fence_async();
        }
        mbar_wait(xempty + (i & 3) * 8, ((i >> 2) & 1) ^ 1);
        if (elect_one()) {
          mbar_expect_tx(xfull + (i & 3) * 8, UNIT);
          if (i < NRS) tma2d(base + (i & 3) * GST_BYTES, &maps.x, ((2 * cj + i) & 15) * 64, rb * 128, xfull + (i & 3) * 8);
          else bulk_load_stream(base + (i & 3) * GST_BYTES, g_act + (uint32_t)(rb * 80 + ((2 * cj + i) & 15)) * UNIT, UNIT, xfull + (i & 3) * 8);
        }
      }
      prefetch_map(&maps.wo);
#pragma unroll 1
      for (int t = 0; t < 4; t++) {
        if (t & 1) mbar_wait(bar_od, t >> 1);
#pragma unroll 1
        for (int p = 0; p < 32768 / OPS; p++) {
          const uint32_t w = p / (16384 / OPS), c = (p / (8192 / OPS)) & 1, off = w * 8192 + (p % (8192 / OPS)) * OPS;
          mbar_wait(bar_ofull + (t & 1) * 16 + w * 8, t >> 1);
          if (elect_one()) {
            bulk_store(g_act + (uint32_t)(rb * 80 + 16 + (cj * 4 + t) * 2 + c) * UNIT + off, base + unit_of(QT, 2 * t + c) + off, OPS);
            asm volatile("cp.async.bulk.commit_group;" ::: "memory");
            asm volatile("cp.async.bulk.wait_group.read %0;" ::"n"(OFL) : "memory");
          }
        }
        if (elect_one()) {
          asm volatile("cp.async.bulk.wait_group.read 0;" ::: "memory");
          mbar_arrive_pred(bar_ofree + t * 8, t < 3);
          asm volatile("cp.async.bulk.wait_group 0;" ::: "memory");
          fence_async();
          red_release(&g_cnt_o[((rb * 4 + t) * 2 + (cj >> 2)) * 32], 2);
        }
        if (t & 1) {
          wait_counter(&g_cnt_o[(rb * 8 + 2 * t - 2 + (cj & 1)) * 32], target);
          wait_counter(&g_cnt_o[(rb * 8 + 2 * t + (cj & 1)) * 32], target);
          if (elect_one()) mbar_arrive_pred(bar_ofree + 24, t == 1);
        }
      }
      wait_counter(&g_cnt_o[(rb * 8 + 7 - (cj & 1)) * 32], target);
      fence_async();
      if (elect_one()) {
        mbar_arrive(bar_cnt);
        PROF(2, true, 27);
        mbar_expect_tx(bar_xres, 32768);
      }
#pragma unroll 1
      for (int u = 0; u < 2; u++) {
        mbar_wait(bar_res, u);
        if (elect_one()) tma2d(base + OFF_RES + u * UNIT, &maps.x, cj * 128 + u * 64, rb * 128, bar_xres);
      }
      const uint32_t tag = epoch % 3 + 1;
      const uint32_t* inbox = g_cand + (lane & 15);
      mbar_wait(bar_ring + 16, 0);
      uint32_t c0 = ld_relaxed(inbox), n = 0;
#define CAND_STEP(cv)                                                                                        \
      {                                                                                                      \
        const bool valid = (cv & 3u) == tag, all = __all_sync(0xffffffffu, valid);                           \
        const uint32_t best = __reduce_max_sync(0xffffffffu, valid ? cv : 0u);                               \
        const uint32_t blk = __ffs(__ballot_sync(0xffffffffu, cv == best)) - 1;                              \
        if (best) sts2(par + PAR_CONST + 56, best, (blk << 7 | (~best >> 2 & 127)) | (all ? 0x1800 : 0x800)); \
        if (all) break;                                                                                      \
        cv = ld_relaxed(inbox);                                                                              \
      }
      while (true) { CAND_STEP(c0) watchdog(n); }
    } else {
      const int t2 = tid - 320;
#pragma unroll 1
      for (int u = 0; u < 2; u++) {
        mbar_wait(bar_hpub + u * 8, 0);
        PROF(1, t2 == 0 && u == 0, 24);
#pragma unroll 1
        for (int c = 0; c < 4; c++) {
          const uint32_t off = u * UNIT + (warp & 1) * 8192 + c * 2048 + lane * 16;
          uint8_t* dst = g_act + (uint32_t)(rb * 80 + cj * 2) * UNIT + off;
          const uint4 v0 = lds4(stage + off), v1 = lds4(stage + off + 512), v2 = lds4(stage + off + 1024), v3 = lds4(stage + off + 1536);
          stg4(dst, v0); stg4(dst + 512, v1); stg4(dst + 1024, v2); stg4(dst + 1536, v3);
        }
        __syncwarp();
        PROF(1, t2 == 0 && u == 0, 15);
        if (lane == 0) red_release(&g_cnt_h[rb * 32 + cj * 2 + u], 1);
        __syncwarp();
        PROF(1, t2 == 0 && u == 0, 25);
      }
      if (lane == 0) {
        mbar_arrive(bar_pread);
        prefetch_map(&maps.wg); prefetch_map(&maps.wu); prefetch_map(&maps.wd); prefetch_map(&maps.out);
      }
      __syncwarp();
      if (b < NFFN) {
        mbar_wait(bar_go2, 0);
        const __nv_bfloat16* pg = ((b & 1) ? P.w_up : P.w_gate) + (b >> 1) * 64 + (size_t)t2 * FF;
        const __nv_bfloat16* pd = P.w_down + (size_t)b * 32768 + t2 * 64;
        PROF(2, t2 == 0, 13);
#pragma unroll 1
        for (int i = 0; i < WN; i += WB) {
          uint32_t v[WB];
#pragma unroll
          for (int u = 0; u < WB; u++) {
            const int k = i + u;
            asm volatile("ld.global.cg.L2::128B.u32 %0, [%1];" : "=r"(v[u]) : "l"(k < 16 ? pg + (size_t)k * 64 * FF : pd + (k - 16) * 4096));
          }
#pragma unroll
          for (int u = 1; u < WB; u++) v[0] ^= v[u];
          sts1(par + PAR_SINK + t2 * 4, v[0]);
        }
        PROF(2, t2 == 0, 14);
      }
      const uint32_t tag = epoch % 3 + 1;
      mbar_wait(bar_go, 0);
      if (warp == 10) {
        const uint32_t* src = g_mod + 2 * DM + cj * 128 + lane * 4;
        const uint2 wr = *reinterpret_cast<const uint2*>(P.w_r + cj * 128 + lane * 4);
        uint4 vga, vsb, vcb, vgb;
        uint32_t n = 0;
        do {
          vga = ld_relaxed4(src); vsb = ld_relaxed4(src + DM); vcb = ld_relaxed4(src + 2 * DM); vgb = ld_relaxed4(src + 3 * DM);
          watchdog(n);
        } while (!__all_sync(0xffffffffu, tag_ok(vga, tag) && tag_ok(vsb, tag) && tag_ok(vcb, tag) && tag_ok(vgb, tag)));
        const float c0 = rbf(1.f + bf_hi(vcb.x)), c1 = rbf(1.f + bf_hi(vcb.y)), c2 = rbf(1.f + bf_hi(vcb.z)), c3 = rbf(1.f + bf_hi(vcb.w));
        const float a0 = c0 * bf_lo(wr.x), a1 = c1 * bf_hi(wr.x), a2 = c2 * bf_lo(wr.y), a3 = c3 * bf_hi(wr.y);
        const uint32_t h0 = pack_bf(a0, a1), h1 = pack_bf(a2, a3);
        const uint32_t t1 = par + PAR_T1 + (lane >> 2) * 64 + (lane & 1) * 32 + (lane & 2) * 2;
        sts1(t1, h0); sts1(t1 + 8, pack_bf(a0 - bf_lo(h0), a1 - bf_hi(h0)));
        sts1(t1 + 16, h1); sts1(t1 + 24, pack_bf(a2 - bf_lo(h1), a3 - bf_hi(h1)));
        sts4(par + PAR_T2 + lane * 32, make_uint4(pack_bf(c0, c1), __byte_perm(vsb.x, vsb.y, 0x7632), __byte_perm(vgb.x, vgb.y, 0x7632), __byte_perm(vga.x, vga.y, 0x7632)));
        sts4(par + PAR_T2 + lane * 32 + 16, make_uint4(pack_bf(c2, c3), __byte_perm(vsb.z, vsb.w, 0x7632), __byte_perm(vgb.z, vgb.w, 0x7632), __byte_perm(vga.z, vga.w, 0x7632)));
      } else {
        const uint4 g = poll4((lane & 2) ? g_mod + 8 - (lane & 1) * 4 : g_mod + 5 * DM + b * 8 + (lane & 1) * 4, tag);
        sts1(par + PAR_CONST + 60, 0);
        if (lane < 2) sts4(par + PAR_CONST + 16 + lane * 16, g);
        else if (lane < 4) sts2(par + PAR_CONST + (lane - 2) * 8, __float_as_uint(untag_sum(g.x, g.y) + untag_sum(g.z, g.w)), epoch);
      }
      __syncwarp();
#pragma unroll 4
      for (int q = XR; q < XE; q++) st_b128(g_xch + ((size_t)b * 8 * 256 + q * 64 + t2) * 4, (epoch & 1) << 16, 0, 0, 0);
      for (int q = 0; q < 2; q++) st_relaxed4(g_stats + ((size_t)cj * SEQ + rb * 128 + q * 64 + t2) * 4, 0, 0, 0, 0);
      if (b < NFFN)
        for (int q = 0; q < 4; q++) st_relaxed4(g_ypart + ((size_t)(q * 32 + (t2 >> 1)) * NFFN + b) * 8 + (t2 & 1) * 4, 0, 0, 0, 0);
      st_relaxed4(g_row + rb * 2 * DM + (t2 >> 5) * DM + cj * 128 + (t2 & 31) * 4, 0, 0, 0, 0);
      __threadfence();
      mbar_arrive(bar_par);
      mbar_wait(bar_gate, 0);
      uint32_t have = 0, n = 0;
      while (true) {
        const uint32_t st = lds1(par + PAR_CONST + 60) >> 7;
        if ((st & 31) != have) {
          const uint32_t* hsrc = g_row + (st & 15) * 2 * DM + t2 * 4;
          uint4 hv[4];
          bool ok = true;
#pragma unroll
          for (int i = 0; i < 4; i++) hv[i] = ld_pairs(hsrc + i * 256);
#pragma unroll
          for (int i = 0; i < 4; i++) {
            sts2(base + ((FT_G >> i * 4) & 15) * UNIT + (warp & 1) * 8192 + 256 + lane * 8, hv[i].x, hv[i].z);
            ok = ok && hv[i].y == tag && hv[i].w == tag;
          }
          have = __all_sync(0xffffffffu, ok) ? st & 31 : 0;
        }
        if ((st ^ have) == 32) break;
        watchdog(n);
      }
      mbar_arrive(bar_sel);
    }
    __syncwarp();
    cluster_arrive();
    {
      const uint32_t tag = epoch % 3 + 1, t3 = tid - 256;
      mbar_wait(bar_win, 0);
      uint2 win = lds2(par + PAR_CONST + 56);
      win.y &= 0x7ff;
      const uint32_t* fsrc = g_row + (win.y >> 7) * 2 * DM + (b >> 1) * 16 + (t3 & 3) * 4 + (b & 1) * 2;
      const uint32_t* ysrc = g_ypart + (size_t)b * NFFN * 8 + min(t3, NFFN - 1) * 4;
      uint2 fh = ld_pair(fsrc), fx = ld_pair(fsrc + DM);
      if (PSL) __nanosleep(PSL);
      uint4 ya = ld_relaxed4(ysrc), yb = ld_relaxed4(ysrc + NFFN * 4);
      const float rwin = __uint_as_float(((int)win.x < 0 ? win.x & 0x7fffffffu : ~win.x) & ~0x1ffu);
      const float rs = rbf(rcp(1.f + __expf(-rbf(rwin))));
      uint32_t n = 0;
      while (__any_sync(0xffffffffu, fh.y != tag || fx.y != tag)) { fh = ld_pair(fsrc); fx = ld_pair(fsrc + DM); watchdog(n); }
      while (!__all_sync(0xffffffffu, tag_ok(ya, tag) && tag_ok(yb, tag))) {
        if (!tag_ok(ya, tag)) ya = ld_relaxed4(ysrc);
        if (!tag_ok(yb, tag)) yb = ld_relaxed4(ysrc + NFFN * 4);
        watchdog(n);
      }
      __syncwarp();
      PROF(8, t3 == 0, 5);
      float y0 = untag_sum(ya.x, yb.x), y1 = untag_sum(ya.y, yb.y), y2 = untag_sum(ya.z, yb.z), y3 = untag_sum(ya.w, yb.w);
      const bool u1 = lane & 2, u2 = lane & 4;
      y0 = (u1 ? y2 : y0) + __shfl_xor_sync(0xffffffffu, u1 ? y0 : y2, 2);
      y1 = (u1 ? y3 : y1) + __shfl_xor_sync(0xffffffffu, u1 ? y1 : y3, 2);
      y0 = (u2 ? y1 : y0) + __shfl_xor_sync(0xffffffffu, u2 ? y0 : y1, 4);
      y0 += __shfl_xor_sync(0xffffffffu, y0, 8);
      if (!(lane & 8)) sts1(par + PAR_RED + 64 + (t3 >> 4) * 32 + ((lane & 1) * 4 + (lane & 2) + ((lane >> 2) & 1)) * 4, __float_as_uint(y0));
      bar_sync(4, 128);
      if (t3 < 4) {
        y0 = 0.f; y1 = 0.f;
#pragma unroll
        for (int w4 = 0; w4 < 7; w4++) {
          const uint2 v = lds2(par + PAR_RED + 64 + w4 * 32 + t3 * 8);
          y0 += __uint_as_float(v.x); y1 += __uint_as_float(v.y);
        }
        const uint2 gv = lds2(par + PAR_CONST + 16 + t3 * 8);
        const uint32_t upd = hmul2(pack_bf(y0, y1), pack_bf(rs, rs));
        *reinterpret_cast<uint32_t*>(P.out + (size_t)win.y * DM + b * 8 + t3 * 2) =
            hadd2(fx.x, hmul2(__byte_perm(gv.x, gv.y, 0x7632), hadd2(fh.x, upd)));
        if (b == 0 && t3 == 0) st_relaxed(&g_epoch, epoch + 1);
      }
      PROF(31, t3 == 0, 36);
    }
    cluster_wait();
  } else {
    const int wg = warp >> 2;

    uint32_t tag;
    {
      uint32_t* const pmod = g_modp + rank * 2 * DM + (b >> 1) * 32 + lane;
      uint32_t* const pln = g_ln1 + (rb * 128 + cj * 16 + warp) * 4;
      const uint32_t cv = ldg_nc1(P.c + rank * 512 + tid * 2);
      const uint32_t epoch = ld_relaxed(&g_epoch);
      if (warp == 0) st_relaxed(pmod, 0);
      if (lane == 0) { st_b128(pln, 0, 0, 0, 0); st_b128(pln + 32, 0, 0, 0, 0); }
      asm volatile("setmaxnreg.inc.sync.aligned.u32 232;");
      sts1(par + tid * 4, pack_bf(silu_f(bf_lo(cv)), silu_f(bf_hi(cv))));
      bar_sync(1, 320);
      tag = epoch % 3 + 1;
#pragma unroll
      for (int part = 0; part < 3; part++) {
        if (part != 1) {
          const uint32_t xa = base + (2 + part / 2) * GST_BYTES + warp * 2048 + lane * 16;
          mbar_wait(bar_hx + part * 4, 0);
          float s0 = 0.f, s1 = 0.f, q0 = 0.f, q1 = 0.f;
#pragma unroll
          for (int q = 0; q < 4; q++) {
            const uint4 xv = lds4(xa + q * 512);
            const uint32_t u[4] = {xv.x, xv.y, xv.z, xv.w};
#pragma unroll
            for (int e = 0; e < 4; e++) { const float lo = bf_lo(u[e]), hi = bf_hi(u[e]); s0 += lo; s1 += hi; q0 += lo * lo; q1 += hi * hi; }
          }
          s0 += s1; q0 += q1;
#pragma unroll
          for (int o = 16; o > 0; o >>= 1) { s0 += __shfl_xor_sync(0xffffffffu, s0, o); q0 += __shfl_xor_sync(0xffffffffu, q0, o); }
          const float mean = s0 * (1.f / DM);
          float mb, sd;
          ln_scalars(mean, fmaxf(q0 * (1.f / DM) - mean * mean, 0.f), mb, sd);
          uint32_t ih, il;
          split_inv(sd, ih, il);
          if (lane == 0) st_b128(pln + part * 16, pack_bf(mb, mb), ih, il, tag);
          PROF(1, tid == 0 && part == 2, 4);
        } else {
          float acc[8];
#pragma unroll
          for (int e = 0; e < 8; e++) acc[e] = 0.f;
          const uint32_t wa = stage + (tid >> 2) * 64 + (((tid ^ (tid >> 3)) & 3) << 4), sa = par + (tid >> 3) * 4, sh = (tid & 4) ? 0x3244 : 0x1044;
          mbar_wait(bar_hw, 0);
#pragma unroll
          for (int p = 0; p < 8; p++) {
            const uint4 w = lds4(wa + p * 4096);
            const float s = __uint_as_float(__byte_perm(lds1(sa + p * 128), 0, sh));
            acc[0] += s * bf_lo(w.x); acc[1] += s * bf_hi(w.x); acc[2] += s * bf_lo(w.y); acc[3] += s * bf_hi(w.y);
            acc[4] += s * bf_lo(w.z); acc[5] += s * bf_hi(w.z); acc[6] += s * bf_lo(w.w); acc[7] += s * bf_hi(w.w);
          }
#pragma unroll
          for (int e = 0; e < 4; e++) {
            const bool up = lane & 16;
            acc[e] = (up ? acc[e + 4] : acc[e]) + __shfl_xor_sync(0xffffffffu, up ? acc[e] : acc[e + 4], 16);
          }
#pragma unroll
          for (int e = 0; e < 2; e++) {
            const bool up = lane & 8;
            acc[e] = (up ? acc[e + 2] : acc[e]) + __shfl_xor_sync(0xffffffffu, up ? acc[e] : acc[e + 2], 8);
          }
          {
            const bool up = lane & 4;
            acc[0] = (up ? acc[1] : acc[0]) + __shfl_xor_sync(0xffffffffu, up ? acc[0] : acc[1], 4);
          }
          sts1(base + 2 * GST_BYTES + warp * 2048 + ((lane & 3) * 8 + (lane >> 2)) * 4, __float_as_uint(acc[0]));
          bar_sync(1, 256);
          if (warp == 0) {
            float s = 0.f;
#pragma unroll
            for (int w8 = 0; w8 < 8; w8++) s += __uint_as_float(lds1(base + 2 * GST_BYTES + w8 * 2048 + lane * 4));
            st_relaxed(pmod, (__float_as_uint(s) & ~3u) | tag);
          }
          PROF(1, tid == 0, 3);
        }
      }
      cluster_wait();
      if (wg == 1) bar_arrive(2, 256);
    }

    float f0 = 0.f, f1 = 0.f;
    const uint32_t rempty = lane < 2 ? mapa(bempty, lane & 1) : 0;
    constexpr uint32_t GE = NSLOT * 8 + 32;
    float o[64], s[64];
#pragma unroll 1
    for (int ps = 0; ps < 3; ps++) {
      {
        const uint32_t xt = ps == 1 ? XT1 : XT2, wt = ps == 1 ? WT1 : WT2;
        const int nst = ps == 2 ? 28 : 14;
        if (ps == 0) {
          float ga[64], gb[64];
#pragma unroll
          for (int i = 0; i < 64; i++) { ga[i] = 0.f; gb[i] = 0.f; }
          uint32_t a[2][16];
          const uint32_t l = fresh_lane();
          uint32_t fa[4];
#pragma unroll
          for (int kk = 0; kk < 4; kk++) fa[kk] = (base + wg * 8192 + frag_offset(warp)) ^ (kk * 32);
          const uint32_t mt = par + (l & 3) * 16;
          auto fetch = [&](int i, uint32_t (&f)[16], uint32_t z) {
            mbar_wait(xfull + (i & 3) * 8, i >> 2);
#pragma unroll
            for (int kk = 0; kk < 4; kk++) ldmatrix4(fa[kk] + (i & 3) * GST_BYTES + z, f[4 * kk], f[4 * kk + 1], f[4 * kk + 2], f[4 * kk + 3]);
          };
          uint4 r0, r1;
          {
            const uint32_t t7 = (warp & 3) * 32 + l;
            const uint32_t* pm = g_modp + wg * DM + ((cj * 128 + t7 * 4) & (DM - 1));
            const uint32_t* pr = g_ln1 + (rb * 128 + warp * 16 + (l >> 2)) * 4;
            uint4 m0 = ld_relaxed4(pm), m1 = ld_relaxed4(pm + 2 * DM);
            r0 = ld_b128(pr); r1 = ld_b128(pr + 32);
            fetch(0, a[0], 0); fetch(1, a[1], 0);
            uint32_t n = 0;
            bool written = false;
#pragma unroll 1
            while (true) {
              uint32_t miss;
              asm volatile("{ .reg .pred p0, p1, p2, p3; .reg .b32 t, u;\n"
                           "lop3.b32 t, %1, %2, %19, 0x7e; lop3.b32 u, %3, %4, %19, 0x7e; or.b32 t, t, u; and.b32 t, t, 3; setp.ne.u32 p0, t, 0;\n"
                           "lop3.b32 t, %5, %6, %19, 0x7e; lop3.b32 u, %7, %8, %19, 0x7e; or.b32 t, t, u; and.b32 t, t, 3; setp.ne.u32 p1, t, 0;\n"
                           "setp.ne.u32 p2, %12, %19; setp.ne.u32 p3, %16, %19;\n"
                           "@p0 ld.relaxed.gpu.global.v4.u32 {%1, %2, %3, %4}, [%17];\n"
                           "@p1 ld.relaxed.gpu.global.v4.u32 {%5, %6, %7, %8}, [%17 + 8192];\n"
                           "@p2 ld.relaxed.gpu.global.v4.u32 {%9, %10, %11, %12}, [%18];\n"
                           "@p3 ld.relaxed.gpu.global.v4.u32 {%13, %14, %15, %16}, [%18 + 128];\n"
                           "or.pred p0, p0, p1; or.pred p2, p2, p3; vote.sync.any.pred p0, p0, 0xffffffff; vote.sync.any.pred p2, p2, 0xffffffff;\n"
                           "selp.u32 t, 1, 0, p0; selp.u32 u, 2, 0, p2; or.b32 %0, t, u; }"
                           : "=r"(miss), "+r"(m0.x), "+r"(m0.y), "+r"(m0.z), "+r"(m0.w), "+r"(m1.x), "+r"(m1.y), "+r"(m1.z), "+r"(m1.w),
                             "+r"(r0.x), "+r"(r0.y), "+r"(r0.z), "+r"(r0.w), "+r"(r1.x), "+r"(r1.y), "+r"(r1.z), "+r"(r1.w)
                           : "l"(pm), "l"(pr), "r"(tag) : "memory");
              if (!(miss & 1) && !written) {
                written = true;
                float c0 = untag_sum(m0.x, m1.x), c1 = untag_sum(m0.y, m1.y), c2 = untag_sum(m0.z, m1.z), c3 = untag_sum(m0.w, m1.w);
                if (wg) { c0 = 1.f + rbf(c0); c1 = 1.f + rbf(c1); c2 = 1.f + rbf(c2); c3 = 1.f + rbf(c3); }
                const uint32_t d = par + (t7 >> 2) * 64 + (t7 & 1) * 32 + (t7 & 2) * 2 + (wg ? 0 : 8);
                sts1(d, pack_bf(c0, c1));
                sts1(d + 16, pack_bf(c2, c3));
                mbar_arrive(bar_mod);
              }
              if (!miss) break;
              watchdog(n);
            }
          }
          const uint32_t zero = r0.w ^ tag;
          auto normalize = [&](uint32_t (&f)[16]) {
#pragma unroll
            for (int k = 0; k < 16; k += 2) { f[k] = ln_norm(f[k], r0.x, r0.y, r0.z); f[k + 1] = ln_norm(f[k + 1], r1.x, r1.y, r1.z); }
          };
          auto modulate = [&](int i, uint32_t (&f)[16]) {
#pragma unroll
            for (int kk = 0; kk < 4; kk++) {
              const uint4 m = lds4(mt + i * 256 + kk * 64);
              f[4 * kk] = MODUL(f[4 * kk], m.x, m.z); f[4 * kk + 1] = MODUL(f[4 * kk + 1], m.x, m.z);
              f[4 * kk + 2] = MODUL(f[4 * kk + 2], m.y, m.w); f[4 * kk + 3] = MODUL(f[4 * kk + 3], m.y, m.w);
            }
            keep(f);
            mbar_arrive_pred(xempty + (i & 3) * 8, l == 0);
          };
          auto publish = [&](int u, uint32_t (&f)[16]) {
#pragma unroll
            for (int kk = 0; kk < 4; kk++) stmatrix4(fa[kk] + OFF_STAGE + u * UNIT, f[4 * kk], f[4 * kk + 1], f[4 * kk + 2], f[4 * kk + 3]);
            __syncwarp();
            mbar_arrive_pred(bar_hpub + u * 8, l == 0);
          };
          auto multiply = [&](int i, uint32_t (&f)[16]) {
            mbar_wait(gfull + (i & 3) * 8, i >> 2);
            const uint64_t db = make_desc(base + (i & 3) * GST_BYTES + UNIT, 8192, 1024);
            wg_fence();
#pragma unroll
            for (int kk = 0; kk < 4; kk++) mma256_rs(ga, gb, f[4 * kk], f[4 * kk + 1], f[4 * kk + 2], f[4 * kk + 3], db + kk * 128);
            wg_commit();
          };
          auto next = [&](int i, uint32_t (&f)[16]) {
            wg_wait<1>();
            mbar_arrive_cl(rempty, GE + ((i + 2) & 3) * 8);
            uint32_t z = zero;
#pragma unroll
            for (int k = 0; k < 16; k += 2) asm volatile("lop3.b32 %0, %1, %2, %0, 0xA8;" : "+r"(z) : "r"(f[k]), "r"(f[k + 1]));
            fetch(i, f, z);
            normalize(f); modulate(i, f); multiply(i, f);
          };
          normalize(a[0]); normalize(a[1]);
          keep(a[0]); keep(a[1]);
          mbar_wait(bar_mod, 0);
          PROF(1, tid == 0, 2);
          if (PORD == 0) { modulate(0, a[0]); multiply(0, a[0]); modulate(1, a[1]); multiply(1, a[1]); publish(0, a[0]); publish(1, a[1]); }
          if (PORD == 1) { modulate(0, a[0]); multiply(0, a[0]); publish(0, a[0]); modulate(1, a[1]); multiply(1, a[1]); publish(1, a[1]); }
          if (PORD == 2) { modulate(0, a[0]); multiply(0, a[0]); publish(0, a[0]); modulate(1, a[1]); publish(1, a[1]); multiply(1, a[1]); }
#pragma unroll 1
          for (int i = 2; i < NRS; i += 2) { next(i, a[0]); next(i + 1, a[1]); }
          wg_wait<1>();
          mbar_arrive_cl(rempty, GE + ((NRS + 2) & 3) * 8);
#pragma unroll 1
          for (int i = NRS; i < 14; i++) {
            mbar_wait(xfull + (i & 3) * 8, (i >> 2) & 1);
            mbar_wait(gfull + (i & 3) * 8, (i >> 2) & 1);
            const uint32_t xa = base + (i & 3) * GST_BYTES;
            const uint64_t da = make_desc(xa + wg * 8192, 16, 1024), db = make_desc(xa + UNIT, 8192, 1024);
            if (i == 13) bar_sync(2 + wg, 256);
            wg_fence();
#pragma unroll
            for (int kk = 0; kk < 4; kk++) mma256_ss(ga, gb, da + kk * 2, db + kk * 128, 1);
            wg_commit();
            if (i == 13) bar_arrive(3 - wg, 256);
            wg_wait<1>();
            uint32_t z = zero;
#pragma unroll
            for (int k = 0; k < 16; k += 2) asm volatile("lop3.b32 %0, %1, %2, %0, 0xA8;" : "+r"(z) : "r"(a[1][k]), "r"(a[1][k + 1]));
            mbar_arrive_cl(rempty, GE + ((i + 3) & 3) * 8 + z);
            mbar_arrive_pred(xempty + ((i + 3) & 3) * 8, l == 0 && i != NRS);
          }
          mbar_wait(xfull + 16, 1);
          wg_wait<0>();
          keep(ga); keep(gb);
#pragma unroll
          for (int i = 0; i < 64; i++) {
            asm volatile("mov.b32 %0, %1;" : "=f"(s[i]) : "f"(ga[i]));
            asm volatile("mov.b32 %0, %1;" : "=f"(o[i]) : "f"(gb[i]));
          }
        } else {
          float ga[64], gb[64];
#pragma unroll
          for (int i = 0; i < 64; i++) {
            asm volatile("mov.b32 %0, %1;" : "=f"(ga[i]) : "f"(s[i]));
            asm volatile("mov.b32 %0, %1;" : "=f"(gb[i]) : "f"(o[i]));
          }
#pragma unroll 1
          for (int i = 0; i < nst; i++) {
            mbar_wait(gfull + (i & 3) * 8, (i >> 2) & 1);
            const uint64_t da = make_desc(base + unit_of(xt, i & 3) + wg * 8192, 16, 1024), db = make_desc(base + unit_of(wt, i & 3), 8192, 1024);
            if (i == nst - 1) bar_sync(2 + wg, 256);
            wg_fence();
#pragma unroll
            for (int kk = 0; kk < 4; kk++) mma256_ss(ga, gb, da + kk * 2, db + kk * 128, kk ? 1 : i);
            wg_commit();
            if (i == nst - 1) bar_arrive(3 - wg, 256);
            wg_wait<1>();
            mbar_arrive_cl(rempty, GE + ((i + 3) & 3) * 8, i != 0);
            PROF(4, tid == 0 && (i & 3) == 0, 40 + (ps - 1) * 4 + i / 4);
          }
          wg_wait<0>();
          keep(ga); keep(gb);
#pragma unroll
          for (int i = 0; i < 64; i++) {
            asm volatile("mov.b32 %0, %1;" : "=f"(s[i]) : "f"(ga[i]));
            asm volatile("mov.b32 %0, %1;" : "=f"(o[i]) : "f"(gb[i]));
          }
        }
        mbar_arrive_cl(rempty, GE + (ps == 2 ? 24 : 8));
        if (ps == 2) break;
      }
      const uint32_t qw = base + wg * 8192, qt = QT >> (16 * ps), at = ps ? AT1 : AT0;
      {
        const uint32_t wt = ps ? WT1 : WT0;
        const uint64_t da0 = make_desc(qw + unit_of(qt, 2), 16, 1024), da1 = make_desc(qw + unit_of(qt, 3), 16, 1024);
        const uint64_t db0 = make_desc(base + unit_of(wt, 2), 8192, 1024), db1 = make_desc(base + unit_of(wt, 3), 8192, 1024);
        mbar_wait(gfull + 16, 1);
        bar_sync(2 + wg, 256);
        wg_fence();
#pragma unroll
        for (int kk = 0; kk < 4; kk++) mma_ss<1>(s, da0 + kk * 2, db0 + kk * 128, 1);
        wg_commit();
        mbar_wait(xfull + 24, 1);
        mbar_wait(gfull + 24, 1);
        wg_fence();
#pragma unroll
        for (int kk = 0; kk < 4; kk++) mma_ss<1>(s, da1 + kk * 2, db1 + kk * 128, 1);
        wg_commit();
        bar_arrive(3 - wg, 256);
        mbar_wait(ps == 0 ? bar_pread : bar_ofree + 8, 0);
        mbar_wait(bfull, 0);
        wg_wait<0>();
        keep(s);
        PROF(2, tid == 0, 8 + ps * 8);
        store_chunk<0>(s, qw + unit_of(qt, 0) + frag_offset(warp));
        store_chunk<1>(s, qw + unit_of(qt, 1) + frag_offset(warp));
        fence_async_smem();
        bar_sync(2 + wg, 256);
        wg_fence();
        issue_qk(s, qw + unit_of(qt, 0), qw + unit_of(qt, 1), base + unit_of(at, 0));
        wg_commit();
#pragma unroll
        for (int kk = 0; kk < 8; kk++) mma_ss<1>(o, (kk < 4 ? da0 : da1) + (kk & 3) * 2, (kk < 4 ? db0 : db1) + UNIT / 16 + (kk & 3) * 128, 1);
        wg_commit();
        bar_arrive(3 - wg, 256);
        wg_wait<1>();
        keep(s);
        mbar_arrive_cl(rempty, 0);
      }
      PROF(4, tid == 0 && ps == 1, 61);
      float l0 = 0.25f, l1 = 0.25f;
      auto step = [&](auto odd_c, const int j, uint32_t (&pw)[32], uint32_t (&pr)[32]) {
        constexpr bool ODD = decltype(odd_c)::value;
        const bool first = !ODD && (j & 2) == 0, last = ODD && j == 7;
        const uint32_t ph = (j >> 1) & 1;
        float i0, i1, a0, a1;
        if (first) { i0 = inv_quad_sum(l0); i1 = inv_quad_sum(l1); l0 = 0.f; l1 = 0.f; }
        bool redo = !ODD && (j | ps) == 0, again = false;
        while (true) {
          if (redo) {
            float m0 = fmaxf(s[0], s[1]), m1 = fmaxf(s[2], s[3]);
#pragma unroll
            for (int i = 1; i < 16; i++) { m0 = fmaxf(m0, fmaxf(s[4 * i], s[4 * i + 1])); m1 = fmaxf(m1, fmaxf(s[4 * i + 2], s[4 * i + 3])); }
            m0 = fmaxf(m0, __shfl_xor_sync(0xffffffffu, m0, 1)); m1 = fmaxf(m1, __shfl_xor_sync(0xffffffffu, m1, 1));
            m0 = fmaxf(m0, __shfl_xor_sync(0xffffffffu, m0, 2)); m1 = fmaxf(m1, __shfl_xor_sync(0xffffffffu, m1, 2));
            m0 *= SCL2; m1 *= SCL2;
            if (!first) {
              m0 = fmaxf(m0, f0); m1 = fmaxf(m1, f1);
              const float c0 = ex2(f0 - m0), c1 = ex2(f1 - m1);
              l0 *= c0; l1 *= c1;
              wg_wait<0>();
              keep(o);
#pragma unroll
              for (int i = 0; i < 16; i++) { o[4 * i] *= c0; o[4 * i + 1] *= c0; o[4 * i + 2] *= c1; o[4 * i + 3] *= c1; }
            }
            f0 = m0; f1 = m1;
          }
          float b0 = 0.f, b1 = 0.f;
          a0 = 0.f; a1 = 0.f;
#pragma unroll
          for (int i = 0; i < 16; i++) {
            const float e0 = ex2(fmaf(s[4 * i], SCL2, -f0)), e1 = ex2(fmaf(s[4 * i + 1], SCL2, -f0));
            const float e2 = ex2(fmaf(s[4 * i + 2], SCL2, -f1)), e3 = ex2(fmaf(s[4 * i + 3], SCL2, -f1));
            a0 += e0; b0 += e1; a1 += e2; b1 += e3;
            pw[2 * i] = pack_bf(e0, e1); pw[2 * i + 1] = pack_bf(e2, e3);
            if (i == VREL) {
#pragma unroll
              for (int k = 0; k < 2 * VREL + 2; k++) asm volatile("" : "+r"(pw[k])::"memory");
              mbar_wait(bar_mod, 0);
              wg_wait<0>();
              mbar_arrive_cl(rempty, ODD ? 16 : (j ? 0 : GE + 16), !again);
              if (!ODD) mbar_arrive_cl(rempty, GE + 24, !again && j == 0);
#pragma unroll
              for (int k = 4 * VREL + 4; k < 64; k++) asm volatile("" : "+f"(s[k])::"memory");
            }
          }
          a0 += b0; a1 += b1;
          if (redo) break;
          redo = __any_sync(0xffffffffu, !(a0 + a1 < 0x1p70f));
          if (first) {
            uint32_t m0 = __ballot_sync(0xffffffffu, a0 > 0x1p-50f), m1 = __ballot_sync(0xffffffffu, a1 > 0x1p-50f);
            m0 |= m0 >> 1; m1 |= m1 >> 1; m0 |= m0 >> 2; m1 |= m1 >> 2;
            redo = redo || (m0 & m1 & 0x11111111u) != 0x11111111u;
          }
          if (!redo) break;
          again = true;
        }
        l0 += a0; l1 += a1;
        keep(pw);
        keep(o);
        const uint32_t qo = qt >> (j ? 0 : 8);
        if (first) store_chunk<0>(o, i0, i1, qw + unit_of(qo, 0) + frag_offset(warp));
        keep(o);
        mbar_wait(bfull + (ODD ? 24 : 8), ph);
        bar_sync(2 + wg, 256);
        if (!last) {
          const uint32_t qn = qt >> (j >= 3 ? 8 : 0);
          wg_fence();
          issue_qk(s, qw + unit_of(qn, 0), qw + unit_of(qn, 1), base + unit_of(at, ODD ? 3 : 1));
          wg_commit();
          mbar_wait(bfull + (ODD ? 0 : 16), ODD ? ph ^ 1 : ph);
        }
        if (first) { store_chunk<1>(o, i0, i1, qw + unit_of(qo, 1) + frag_offset(warp)); keep(o); }
        wg_fence();
        issue_pv(o, pw, base + unit_of(at, ODD ? (last ? 3 : 0) : 2), !first);
        wg_commit();
        bar_arrive(3 - wg, 256);
        wg_wait<1>();
        keep(s);
        mbar_arrive_cl(rempty, ODD ? 24 : 8, !last);
        if (first) { fence_async_smem(); mbar_arrive_pred(bar_ofull + wg * 8, j); }
        PROF(4, tid == 0 && ps == 1, 51 + j);
      };
      uint32_t pa[32], pb[32];
#pragma unroll 1
      for (int j = 0; j < 8; j += 2) {
        step(std::false_type{}, j, pa, pb);
        step(std::true_type{}, j + 1, pb, pa);
      }
      {
        const float i0 = inv_quad_sum(l0), i1 = inv_quad_sum(l1);
        wg_wait<0>();
        keep(o);
        mbar_arrive_cl(rempty, 24);
        store_chunk<0>(o, i0, i1, qw + unit_of(qt, 2) + frag_offset(warp));
        store_chunk<1>(o, i0, i1, qw + unit_of(qt, 3) + frag_offset(warp));
        fence_async_smem();
        mbar_arrive(bar_ofull + 16 + wg * 8);
      }
      PROF(2, tid == 0, 10 + ps * 8);
    }

    const int ln = fresh_lane(), g = ln >> 2, tq = ln & 3, ct = warp * 32 + ln;
    const bool lane0 = ln == 0;
    const int lrow0 = warp * 16 + g;
    const int grow0 = rb * 128 + lrow0;
    const uint32_t res = base + OFF_RES, trow = res + wg * 8192 + frag_offset(warp);
    uint32_t xr[32];
    uint4 sv[4], own;
    uint32_t* sp[4];
#pragma unroll
    for (int k = 0; k < 4; k++) sp[k] = g_stats + ((((tq >> 1) * 4 + k) ^ cj) * SEQ + grow0 + (tq & 1) * 8) * 4;
    {
      const uint64_t da = make_desc(base + wg * 8192, 16, 1024), db = make_desc(base, 8192, 1024);
      constexpr int U = UNIT / 16;
#define HALF_STAGE(acc, xu, wu) _Pragma("unroll") for (int kk = 0; kk < 4; kk++) mma_ss<1>(acc, da + (xu) * U + kk * 2, db + (wu) * U + kk * 128, 1)
      PROF(10, ct == PT, 19); STAMP(0);
      cluster_arrive();
      mbar_wait(gfull, 1);
      mbar_wait(gfull + 8, 1);
      bar_sync(2 + wg, 256);
      wg_fence();
      HALF_STAGE(o, 7, 1);
      HALF_STAGE(o, 8, 3);
      wg_commit();
      STAMP(16);
      mbar_wait(gfull + 16, 1);
      STAMP(17);
      wg_fence();
      HALF_STAGE(o, 6, 11);
      wg_commit();
      bar_arrive(3 - wg, 256);
      mbar_wait(bar_par, 0);
      uint32_t* xo = g_xch + ((size_t)b * 8 * 256 + ct) * 4;
      const uint32_t* xi = g_xch + ((size_t)(b ^ 2) * 8 * 256 + ct) * 4;
      const uint32_t par1 = (~lds1(par + PAR_CONST + 4) & 1) << 16;
      uint32_t ga[16];
      uint4 bw[8];
#define LOAD_PAR _Pragma("unroll") for (int i = 0; i < 8; i++) {                                                               \
        ga[2 * i] = lds1(par + PAR_T2 + i * 128 + tq * 16 + 12); ga[2 * i + 1] = lds1(par + PAR_T2 + i * 128 + 64 + tq * 16 + 12); \
        bw[i] = lds4(par + PAR_T1 + i * 64 + tq * 16);                                                                          \
        if (!(g & 1)) { bw[i].x = 0x3f803f80u; bw[i].y = 0x3f803f80u; }                                                         \
      }
      if (PPOS == 0) LOAD_PAR
      wg_wait<1>();
      mbar_arrive_pred(bar_rel, lane0);
      wg_wait<0>();
      keep(o);
      mbar_arrive_pred(bar_ring, lane0);
      PROF(8, ct == PT, 20); STAMP(1);
#define SEND(i) st_b128(xo + (i) * 1024, (pack_bf(o[8 * (i)], o[8 * (i) + 1]) & ~0x10000u) | par1, pack_bf(o[8 * (i) + 2], o[8 * (i) + 3]), \
                        pack_bf(o[8 * (i) + 4], o[8 * (i) + 5]), pack_bf(o[8 * (i) + 6], o[8 * (i) + 7]))
#pragma unroll
      for (int i = 0; i < NS1; i++) SEND(i);
      PROF(8, ct == PT, 21); STAMP(2);
      bar_sync(2 + wg, 256);
      wg_fence();
      HALF_STAGE(s, 7, 0);
      HALF_STAGE(s, 8, 2);
      HALF_STAGE(s, 6, 10);
      wg_commit();
      bar_arrive(3 - wg, 256);
      STAMP(18);
      mbar_wait(gfull + 24, 1);
#pragma unroll
      for (int i = NS1; i < 8; i++) SEND(i);
      uint4 v[8];
#pragma unroll
      for (int i = 0; i < 4; i++) v[i] = ld_b128(xi + i * 1024);
      if (PPOS == 1) LOAD_PAR
      STAMP(19);
      mbar_wait(bar_xres, 0);
      wg_wait<0>();
      mbar_arrive_pred(bar_ring + 8, lane0);
      bar_sync(2 + wg, 256);
      STAMP(20);
#pragma unroll
      for (int i = 4; i < 8; i++) v[i] = ld_b128(xi + i * 1024);
      mbar_wait(bar_xres, 0);
      wg_fence();
      HALF_STAGE(s, 9, 4);
      wg_commit();
      mbar_wait(bar_rx, 0);
      wg_fence();
      HALF_STAGE(s, 1, 5);
      wg_commit();
      bar_arrive(3 - wg, 256);
      STAMP(21);
      wg_wait<0>();
      keep(s);
      mbar_arrive_pred(bar_ring + 16, lane0);
      PROF(10, ct == PT, 23); STAMP(4);
#pragma unroll
      for (int i = 0; i < 16; i += 2) ldmatrix4((trow ^ ((i & 7) << 4)) + (i >> 3) * 16384, xr[2 * i], xr[2 * i + 1], xr[2 * i + 2], xr[2 * i + 3]);
      if (PPOS == 2) LOAD_PAR
      uint32_t pk[32];
      pack_p(s, pk);
      keep(pk);
      {
        uint32_t n = 0, miss;
        do {
          miss = 0;
#pragma unroll
          for (int i = 0; i < 8; i++) miss |= v[i].x ^ par1;
          miss = __any_sync(0xffffffffu, miss & 0x10000u);
          if (miss) {
#pragma unroll
            for (int i = 0; i < 8; i++)
              asm volatile("{ .reg .pred p; .reg .b32 t; xor.b32 t, %0, %5; and.b32 t, t, 0x10000; setp.ne.u32 p, t, 0;\n"
                           "@p ld.relaxed.gpu.global.v4.u32 {%0, %1, %2, %3}, [%4]; }"
                           : "+r"(v[i].x), "+r"(v[i].y), "+r"(v[i].z), "+r"(v[i].w) : "l"(xi + i * 1024), "r"(par1) : "memory");
          }
          watchdog(n);
        } while (miss);
      }
      PROF(8, ct == PT, 22); STAMP(3);
#pragma unroll
      for (int k = 0; k < 4; k++) sv[k] = ESV ? ld_b128(sp[k]) : make_uint4(0, 0, 0, 0);
      float ds[4] = {0.f, 0.f, 0.f, 0.f}, dl[4] = {0.f, 0.f, 0.f, 0.f}, q0[4] = {0.f, 0.f, 0.f, 0.f}, q1[4] = {0.f, 0.f, 0.f, 0.f};
#pragma unroll
      for (int i = 0; i < 8; i++) {
        const uint32_t u0 = hfma2(ga[2 * i], hadd2(pk[4 * i], v[i].x & ~0x10000u), xr[4 * i]);
        const uint32_t u1 = hfma2(ga[2 * i], hadd2(pk[4 * i + 1], v[i].y), xr[4 * i + 1]);
        const uint32_t u2 = hfma2(ga[2 * i + 1], hadd2(pk[4 * i + 2], v[i].z), xr[4 * i + 2]);
        const uint32_t u3 = hfma2(ga[2 * i + 1], hadd2(pk[4 * i + 3], v[i].w), xr[4 * i + 3]);
        xr[4 * i] = u0; xr[4 * i + 1] = u1; xr[4 * i + 2] = u2; xr[4 * i + 3] = u3;
        mma16816(ds, u0, u1, u2, u3, bw[i].x, bw[i].y);
        mma16816(dl, u0, u1, u2, u3, bw[i].z, bw[i].w);
        mma16816(q0, u0, u1, u2, u3, u0, u2);
        mma16816(q1, u0, u1, u2, u3, u1, u3);
      }
      const float sqa = __shfl_sync(0xffffffffu, (g & 1) ? q0[1] : q0[0], g * 4 + (g >> 1));
      const float sqb = __shfl_sync(0xffffffffu, (g & 1) ? q1[3] : q1[2], g * 4 + (g >> 1));
      own = (tq & 1) ? make_uint4(__float_as_uint(ds[2]), __float_as_uint(sqb), __float_as_uint(ds[3] + dl[3]), tag)
                                 : make_uint4(__float_as_uint(ds[0]), __float_as_uint(sqa), __float_as_uint(ds[1] + dl[1]), tag);
      if (tq < 2) st_b128(sp[0], own.x, own.y, own.z, own.w);
    }
    PROF(8, ct == PT, 29); STAMP(5);
    uint32_t mm, ih, il;
    float rbest;
    uint32_t wf[128];
    const uint32_t frow = (ln & 7) + (ln >> 4) * 8;
    const uint32_t wfo = base + (warp & 1) * 8192 + frow * 64 + ((((ln >> 3) & 1) ^ ((frow >> 1) & 3)) << 4);
#define LOAD_WF(m) _Pragma("unroll") for (int f = 0; f < 16; f++) {                                                   \
      const int r = ((f >> 1) * 4 + (m) * 2 + (f & 1)) * 4;                                                           \
      ldmatrix4t(((wfo + unit_of((m) ? FT_U : FT_G, warp >> 1)) ^ ((f & 1) * 32)) + (f >> 1) * 1024, wf[r], wf[r + 1], wf[r + 2], wf[r + 3]); \
    }
    bool early, wait1;
    {
#pragma unroll
      for (int i = 0; i < 16; i += 2) stmatrix4((trow ^ ((i & 7) << 4)) + (i >> 3) * 16384, xr[2 * i], xr[2 * i + 1], xr[2 * i + 2], xr[2 * i + 3]);
      const uint4 cst = lds4(par + PAR_CONST);
      const float A1 = __uint_as_float(cst.x), A2 = __uint_as_float(cst.z);
      uint32_t n = 0;
      early = false; wait1 = false;
#pragma unroll 1
      while (true) {
        uint32_t miss;
        asm volatile("{ .reg .pred p0, p1, p2, p3; .reg .b64 u, v; .reg .b128 w;\n"
                     "setp.ge.u32 p0, %22, 2; setp.ne.and.u32 p0, %4, %21, p0; setp.ne.u32 p1, %8, %21; setp.ne.u32 p2, %12, %21; setp.ne.u32 p3, %16, %21;\n"
                     "@p0 ld.relaxed.gpu.global.v4.u32 {%1, %2, %3, %4}, [%17];\n"
                     "@p1 ld.relaxed.gpu.global.v4.u32 {%5, %6, %7, %8}, [%18];\n"
                     "@p2 ld.relaxed.gpu.global.v4.u32 {%9, %10, %11, %12}, [%19];\n"
                     "@p3 ld.relaxed.gpu.global.v4.u32 {%13, %14, %15, %16}, [%20];\n"
                     "or.pred p0, p0, p1; or.pred p2, p2, p3; or.pred p0, p0, p2; vote.sync.any.pred p0, p0, 0xffffffff; selp.u32 %0, 1, 0, p0; }"
                     : "=r"(miss), "+r"(sv[0].x), "+r"(sv[0].y), "+r"(sv[0].z), "+r"(sv[0].w), "+r"(sv[1].x), "+r"(sv[1].y), "+r"(sv[1].z), "+r"(sv[1].w),
                       "+r"(sv[2].x), "+r"(sv[2].y), "+r"(sv[2].z), "+r"(sv[2].w), "+r"(sv[3].x), "+r"(sv[3].y), "+r"(sv[3].z), "+r"(sv[3].w)
                     : "l"(sp[0]), "l"(sp[1]), "l"(sp[2]), "l"(sp[3]), "r"(tag), "r"(tq) : "memory");
        if (!miss) break;
        wait1 = true;
        if (!early && (b >= NFFN || __all_sync(0xffffffffu, mbar_test(bar_box + (warp >> 1) * 8, 0)))) {
          early = true;
          LOAD_WF(0);
          __syncwarp();
          mbar_arrive_pred(bar_gate, lane0);
        }
        watchdog(n);
      }
      const uint4 v0 = tq < 2 ? own : sv[0], v1 = sv[1], v2 = sv[2], v3 = sv[3];
      PROF(8, ct == PT, 30); STAMP(6);
      float su = (__uint_as_float(v0.x) + __uint_as_float(v1.x)) + (__uint_as_float(v2.x) + __uint_as_float(v3.x));
      float sq = (__uint_as_float(v0.y) + __uint_as_float(v1.y)) + (__uint_as_float(v2.y) + __uint_as_float(v3.y));
      float dt = (__uint_as_float(v0.z) + __uint_as_float(v1.z)) + (__uint_as_float(v2.z) + __uint_as_float(v3.z));
      su += __shfl_xor_sync(0xffffffffu, su, 2); sq += __shfl_xor_sync(0xffffffffu, sq, 2); dt += __shfl_xor_sync(0xffffffffu, dt, 2);
      const float m = su * (1.f / DM);
      float mb, sd;
      ln_scalars(m, fmaxf(sq * (1.f / DM) - m * m, 0.f), mb, sd);
      const float inv = rcp(sd);
      rbest = (dt - mb * A1) * inv + A2;
      mm = pack_bf(mb, mb);
      ih = pack_bf(inv, inv);
      const float lo = inv - bf_lo(ih);
      il = pack_bf(lo, lo);
    }
    int ibest;
    {
      const uint32_t bits = __float_as_uint(rbest);
      const uint32_t key = (((int)bits < 0 ? ~bits : bits | 0x80000000u) & ~0x1ffu) | ((127 - lrow0 - (tq & 1) * 8) << 2) | tag;
      sts1(par + PAR_RED + warp * 4, __reduce_max_sync(0xffffffffu, key));
      PROF(8, ct == PT, 38); STAMP(7);
      uint32_t waited;
      asm volatile("{ .reg .pred p, q; setp.ne.u32 p, %1, 0; barrier.cta.red.or.pred q, 1, 256, p; selp.u32 %0, 1, 0, q; }" : "=r"(waited) : "r"((uint32_t)(wait1 && (wg || CW0))) : "memory");
      const uint4 ka = lds4(par + PAR_RED), kb = lds4(par + PAR_RED + 16);
      const uint32_t k2 = max(max(max(ka.x, ka.y), max(ka.z, ka.w)), max(max(kb.x, kb.y), max(kb.z, kb.w)));
      if (ct == 0 && ((cj & CWM) == 0 || (CWL && !waited))) st_relaxed(g_cand + rb, k2);
      ibest = 127 - ((k2 >> 2) & 127);
    }
    PROF(8, ct == PT, 39); STAMP(8);
    if ((ibest >> 4) == warp) {
      const int src = (ibest & 7) * 4 + ((ibest >> 3) & 1), ch = g * 2;
      const uint32_t cm = __shfl_sync(0xffffffffu, mm, src), ch_ = __shfl_sync(0xffffffffu, ih, src), cl = __shfl_sync(0xffffffffu, il, src);
      const uint32_t xa = res + (ch >> 3) * 16384 + ibest * 128 + (((ch & 7) ^ (ibest & 7)) << 4) + tq * 4;
      const uint32_t x0 = lds1(xa), x1 = lds1(xa ^ 16);
      const uint2 p0 = lds2(par + PAR_T2 + ch * 64 + tq * 16), p1 = lds2(par + PAR_T2 + ch * 64 + 64 + tq * 16);
      uint32_t* dst = g_row + rb * 2 * DM + cj * 128 + ln * 4;
      st_pairs(dst, ln_mod(x0, cm, ch_, cl, p0.x, p0.y), ln_mod(x1, cm, ch_, cl, p1.x, p1.y), tag);
      st_pairs(dst + DM, x0, x1, tag);
      __syncwarp();
    }
    PROF(8, ct == PT, 37); STAMP(9);
    uint32_t wd[64];
    const uint32_t wda = base + unit_of(FT_D, warp >> 1) + (warp & 1) * 8192 + frow * 128 + ((((ln >> 3) & 1) ^ (ln & 7)) << 4);
#define LOAD_WD(f) ldmatrix4t((wda ^ ((((f) >> 1) & 3) * 32)) + ((f) >> 3) * 4096 + ((f) & 1) * 2048, wd[4 * (f)], wd[4 * (f) + 1], wd[4 * (f) + 2], wd[4 * (f) + 3])
    if (!early) {
      if (b < NFFN) mbar_wait(bar_box + (warp >> 1) * 8, 0);
      LOAD_WF(0);
      __syncwarp();
      mbar_arrive_pred(bar_gate, lane0);
    }
    if (b < NFFN) {
      const uint32_t own = base + unit_of(FT_G, warp >> 1) + (warp & 1) * 8192;
      mbar_wait(bar_box + (4 + (warp >> 1)) * 8, 0);
      LOAD_WF(1);
      uint32_t* const ydst = g_ypart + ((size_t)(warp * 16 + tq * 2) * NFFN + b) * 8 + g;
      PROF(8, ct == PT, 31); STAMP(10);
      mbar_wait(bar_box + (8 + (warp >> 1)) * 8, 0);
#pragma unroll
      for (int f = 0; f < WDE; f++) LOAD_WD(f);
      STAMP(11);
      mbar_wait(bar_sel, 0);
      PROF(8, ct == PT, 33); STAMP(12);
      float d[8][4];
#pragma unroll
      for (int i = 0; i < 4; i++) { d[i][0] = 0.f; d[i][1] = 0.f; d[i][2] = 0.f; d[i][3] = 0.f; }
#pragma unroll
      for (int ks = 0; ks < 8; ks++) {
        const uint2 hb = lds2(own + 256 + ks * 32 + tq * 8);
#pragma unroll
        for (int mt = 0; mt < 4; mt++) {
          const int r = ks * 16 + mt * 4;
          mma16816(d[mt], wf[r], wf[r + 1], wf[r + 2], wf[r + 3], hb.x, hb.y);
        }
      }
      sts2(own + (tq * 8 + g) * 8, __float_as_uint((tq & 2) ? ((tq & 1) ? d[1][2] : d[1][0]) : ((tq & 1) ? d[0][2] : d[0][0])),
           __float_as_uint((tq & 2) ? ((tq & 1) ? d[3][2] : d[3][0]) : ((tq & 1) ? d[2][2] : d[2][0])));
      bar_sync(1, 256);
      uint32_t ab[4];
      {
        float G = 0.f, U = 0.f;
        uint2 pv[8];
#pragma unroll
        for (int w8 = 0; w8 < 8; w8++) pv[w8] = lds2(base + ln * 8 + ((FT_G >> (w8 >> 1) * 4) & 15) * UNIT + (w8 & 1) * 8192);
#pragma unroll
        for (int w8 = 0; w8 < 8; w8 += 2) {
          G += __uint_as_float(pv[w8].x) + __uint_as_float(pv[w8 + 1].x);
          U += __uint_as_float(pv[w8].y) + __uint_as_float(pv[w8 + 1].y);
        }
#pragma unroll
        for (int f = WDE; f < 16; f++) LOAD_WD(f);
        const float act = rbf(silu_f(rbf(G))) * rbf(U);
        const uint32_t pk = pack_bf(act, __shfl_down_sync(0xffffffffu, act, 1));
#pragma unroll
        for (int i = 0; i < 4; i++) ab[i] = __shfl_sync(0xffffffffu, pk, i * 8 + tq * 2);
      }
      PROF(8, ct == PT, 34); STAMP(13);
#pragma unroll
      for (int mt = 0; mt < 8; mt++) {
        d[mt][0] = 0.f; d[mt][1] = 0.f; d[mt][2] = 0.f; d[mt][3] = 0.f;
        mma16816(d[mt], wd[mt * 8], wd[mt * 8 + 1], wd[mt * 8 + 2], wd[mt * 8 + 3], ab[0], ab[1]);
        mma16816(d[mt], wd[mt * 8 + 4], wd[mt * 8 + 5], wd[mt * 8 + 6], wd[mt * 8 + 7], ab[2], ab[3]);
      }
#pragma unroll
      for (int i = 0; i < 4; i++) {
        const int m4 = (i >> 1) * 4, e = (i & 1) * 2;
        const float y = (tq & 2) ? ((tq & 1) ? d[m4 + 3][e] : d[m4 + 2][e]) : ((tq & 1) ? d[m4 + 1][e] : d[m4][e]);
        st_relaxed(ydst + (m4 * 2 + (i & 1)) * NFFN * 8, tagf(y, tag));
      }
      PROF(8, ct == PT, 35); STAMP(14);
    }
    mbar_wait(bar_sel, 0);
    mbar_arrive_pred(bar_win, ct == 0);
    const int iwin = lds1(par + PAR_CONST + 60) & 0x7ff;
    {
      const uint32_t mm0 = __shfl_sync(0xffffffffu, mm, ln & ~1), mm1 = __shfl_sync(0xffffffffu, mm, ln | 1);
      const uint32_t ih0 = __shfl_sync(0xffffffffu, ih, ln & ~1), ih1 = __shfl_sync(0xffffffffu, ih, ln | 1);
      const uint32_t il0 = __shfl_sync(0xffffffffu, il, ln & ~1), il1 = __shfl_sync(0xffffffffu, il, ln | 1);
      const bool mine = (iwin >> 4) == rb * 8 + warp;
#pragma unroll 1
      for (int hf = 0; hf < 2; hf++) {
        uint32_t x[16];
#pragma unroll
        for (int i = 0; i < 8; i += 2) ldmatrix4((trow ^ (i << 4)) + hf * 16384, x[2 * i], x[2 * i + 1], x[2 * i + 2], x[2 * i + 3]);
#pragma unroll
        for (int i = 0; i < 8; i++) {
          const uint4 pv = lds4(par + PAR_T2 + (hf * 8 + i) * 64 + tq * 16);
          x[2 * i] = hadd2(x[2 * i], hmul2(pv.z, ln_mod(x[2 * i], mm0, ih0, il0, pv.x, pv.y)));
          x[2 * i + 1] = hadd2(x[2 * i + 1], hmul2(pv.z, ln_mod(x[2 * i + 1], mm1, ih1, il1, pv.x, pv.y)));
        }
        if (mine) {
          uint32_t* dst = reinterpret_cast<uint32_t*>(P.out + (size_t)grow0 * DM + cj * 128 + hf * 64) + tq;
#pragma unroll
          for (int i = 0; i < 8; i++) {
            if (grow0 != iwin) dst[i * 4] = x[2 * i];
            if (grow0 + 8 != iwin) dst[i * 4 + 4 * DM] = x[2 * i + 1];
          }
        } else {
#pragma unroll
          for (int i = 0; i < 8; i += 2) stmatrix4((trow ^ (i << 4)) + hf * 16384, x[2 * i], x[2 * i + 1], x[2 * i + 2], x[2 * i + 3]);
          fence_async_smem();
          __syncwarp();
          if (elect_one()) {
            tma2d_store(&maps.out, res + hf * 16384 + warp * 2048, cj * 128 + hf * 64, rb * 128 + warp * 16);
            asm volatile("cp.async.bulk.commit_group;" ::: "memory");
          }
        }
      }
      asm volatile("cp.async.bulk.wait_group.read 0;" ::: "memory");
    }
    PROF(8, ct == PT, 11); STAMP(15);
    cluster_wait();
  }
}

typedef CUresult (*EncodeFn)(CUtensorMap*, CUtensorMapDataType, cuuint32_t, void*, const cuuint64_t*, const cuuint64_t*,
                             const cuuint32_t*, const cuuint32_t*, CUtensorMapInterleave, CUtensorMapSwizzle,
                             CUtensorMapL2promotion, CUtensorMapFloatOOBfill);

void map2d(EncodeFn enc, CUtensorMap* m, const void* p, uint64_t rows, uint64_t cols, uint32_t brows) {
  cuuint64_t dims[2] = {cols, rows}, strides[1] = {cols * 2};
  cuuint32_t box[2] = {64, brows}, es[2] = {1, 1};
  enc(m, CU_TENSOR_MAP_DATA_TYPE_BFLOAT16, 2, const_cast<void*>(p), dims, strides, box, es, CU_TENSOR_MAP_INTERLEAVE_NONE,
      CU_TENSOR_MAP_SWIZZLE_128B, CU_TENSOR_MAP_L2_PROMOTION_L2_256B, CU_TENSOR_MAP_FLOAT_OOB_FILL_NONE);
}
void map2d_narrow(EncodeFn enc, CUtensorMap* m, const void* p, uint64_t rows, uint64_t cols, uint32_t brows) {
  cuuint64_t dims[2] = {cols, rows}, strides[1] = {cols * 2};
  cuuint32_t box[2] = {32, brows}, es[2] = {1, 1};
  enc(m, CU_TENSOR_MAP_DATA_TYPE_BFLOAT16, 2, const_cast<void*>(p), dims, strides, box, es, CU_TENSOR_MAP_INTERLEAVE_NONE,
      CU_TENSOR_MAP_SWIZZLE_64B, CU_TENSOR_MAP_L2_PROMOTION_L2_64B, CU_TENSOR_MAP_FLOAT_OOB_FILL_NONE);
}
void map3d(EncodeFn enc, CUtensorMap* m, const void* p, uint64_t rows, uint64_t cols, uint32_t brows, uint32_t nch) {
  cuuint64_t dims[3] = {64, rows, cols / 64}, strides[2] = {cols * 2, 128};
  cuuint32_t box[3] = {64, brows, nch}, es[3] = {1, 1, 1};
  enc(m, CU_TENSOR_MAP_DATA_TYPE_BFLOAT16, 3, const_cast<void*>(p), dims, strides, box, es, CU_TENSOR_MAP_INTERLEAVE_NONE,
      CU_TENSOR_MAP_SWIZZLE_128B, CU_TENSOR_MAP_L2_PROMOTION_L2_256B, CU_TENSOR_MAP_FLOAT_OOB_FILL_NONE);
}

}

extern "C" void kernel_launch(void* const* d_in, const int* in_sizes, int n_in, void* d_out, int out_size) {
  (void)in_sizes; (void)n_in; (void)out_size;
  static EncodeFn enc = nullptr;
  if (!enc) {
    void* fn = nullptr;
    cudaDriverEntryPointQueryResult st;
    cudaGetDriverEntryPoint("cuTensorMapEncodeTiled", &fn, cudaEnableDefault, &st);
    enc = (EncodeFn)fn;
    cudaFuncSetAttribute(fused_kernel, cudaFuncAttributeMaxDynamicSharedMemorySize, SMEM_BYTES);
  }
  Maps maps;
  map2d(enc, &maps.x, d_in[0], SEQ, DM, 128);
  map2d(enc, &maps.out, d_out, SEQ, DM, 16);
  map3d(enc, &maps.wq, d_in[3], DM, NQ, 64, 2);
  map3d(enc, &maps.k, d_in[1], 4 * SK, 128, 128, 1);
  map3d(enc, &maps.v, d_in[2], 4 * SK, 128, 128, 1);
  map3d(enc, &maps.wo, d_in[4], NQ, DM, 64, 2);
  map2d_narrow(enc, &maps.wg, d_in[7], DM, FF, 256);
  map2d_narrow(enc, &maps.wu, d_in[8], DM, FF, 256);
  map3d(enc, &maps.wd, d_in[9], FF, DM, 32, 4);
  map2d_narrow(enc, &maps.wm, d_in[11], DM, NMOD, 256);
  Ptrs p;
  p.x = (const __nv_bfloat16*)d_in[0];
  p.w_r = (const __nv_bfloat16*)d_in[6];
  p.w_gate = (const __nv_bfloat16*)d_in[7];
  p.w_up = (const __nv_bfloat16*)d_in[8];
  p.w_down = (const __nv_bfloat16*)d_in[9];
  p.c = (const __nv_bfloat16*)d_in[10];
  p.w_mod = (const __nv_bfloat16*)d_in[11];
  p.out = (__nv_bfloat16*)d_out;
  fused_kernel<<<NMAIN + NHELP, 384, SMEM_BYTES>>>(maps, p);
}
```

```cpp
#include <cuda_runtime.h>
#include <cuda_bf16.h>
#include <cuda.h>
#include <stdint.h>
#include <type_traits>

#define HD 2
#define HDX 2
#define XF 4
#define XE 32
#define XR 0
#define NRS 8
#define FPACE 3
#define GOST 20
#define WB 3
#define WN 24
#define RES0 17
#define RES1 20
#define HU 32
#define NS1 6
#define PG0 0
#define PSL 0
#define CWM 7
#define WDE 16
#define CWL 1
#define CW0 0
#define ESV 1
#define PPOS 1
#define FB0 0
#define FB2 8
#define OPS 8192
#define OFL 0
#define ODS 8
#define MODUL hfma2
#define VREL 7
#define E0 3

namespace {

constexpr int SEQ = 2048, DM = 1024, NQ = 4096, SK = 2048, WIN = 512, FF = 3584, NMOD = 6144;
constexpr int NMAIN = 128, NHELP = 4, NFFN = 112;
constexpr int NSLOT = 4, SLOT_BYTES = 32768, UNIT = 16384, GST_BYTES = 3 * UNIT;
constexpr uint32_t XT1 = 0xDCBA, XT2 = 0x9687;
constexpr uint32_t WT0 = 0xA741, WT1 = 0x7420, WT2 = 0x4A20;
constexpr uint32_t AT0 = WT1, AT1 = WT2;
constexpr uint32_t QT = 0xDC9696DC;
constexpr int OFF_STAGE = 12 * UNIT;
constexpr uint32_t FT_G = 0x07B3, FT_U = 0xA628, FT_D = 0x5149;
constexpr int OFF_RES = 12 * UNIT;
constexpr int OFF_PAR = 14 * UNIT;
constexpr int OFF_BAR = OFF_PAR + 2528;
constexpr int SMEM_BYTES = OFF_BAR + 544;
static_assert(SMEM_BYTES <= 232448, "smem");

constexpr int PAR_T1 = 0;
constexpr int PAR_T2 = 512;
constexpr int PAR_CONST = 1536;
constexpr int PAR_RED = 1600;
constexpr int PAR_SINK = 2176;

struct Maps {
  CUtensorMap x, wq, k, v, wo, wg, wu, wd, wm, out;
};
struct Ptrs {
  const __nv_bfloat16 *x, *w_r, *c, *w_mod, *w_gate, *w_up, *w_down;
  __nv_bfloat16* out;
};

__device__ __align__(1024) uint8_t g_act[16 * 80 * UNIT];
__device__ __align__(128) uint32_t g_mod[NMOD];
__device__ __align__(128) uint32_t g_modp[2 * 2 * DM];
__device__ __align__(128) uint32_t g_ln1[SEQ * 4];
__device__ __align__(128) uint32_t g_cnt_h[16 * 32];
__device__ __align__(128) uint32_t g_cnt_o[128 * 32];
__device__ __align__(128) uint32_t g_xch[NMAIN * 8 * 256 * 4];
__device__ __align__(128) uint32_t g_stats[8 * SEQ * 4];
__device__ __align__(128) uint32_t g_cand[32];
__device__ __align__(128) uint32_t g_row[16 * 2 * DM];
__device__ __align__(128) uint32_t g_ypart[NMAIN * NFFN * 8];
__device__ uint32_t g_epoch;

__device__ __forceinline__ uint32_t fresh_lane() { uint32_t l; asm volatile("mov.u32 %0, %%laneid;" : "=r"(l)); return l; }
__device__ __forceinline__ uint32_t frag_offset(int warp) {
  const uint32_t l = fresh_lane();
  return ((warp & 3) * 16 + (l & 15)) * 128 + (((l >> 4) ^ (l & 7)) << 4);
}
__device__ __forceinline__ bool elect_one() {
  uint32_t p;
  asm volatile("{ .reg .pred q; elect.sync _|q, 0xffffffff; selp.u32 %0, 1, 0, q; }" : "=r"(p));
  return p;
}
__device__ __forceinline__ uint32_t smem_u32(const void* p) { return (uint32_t)__cvta_generic_to_shared(p); }
__device__ __forceinline__ void mbar_init(uint32_t bar, uint32_t cnt) {
  asm volatile("mbarrier.init.shared::cta.b64 [%0], %1;" ::"r"(bar), "r"(cnt) : "memory");
}
__device__ __forceinline__ void mbar_expect_tx(uint32_t bar, uint32_t bytes) {
  asm volatile("mbarrier.arrive.expect_tx.shared::cta.b64 _, [%0], %1;" ::"r"(bar), "r"(bytes) : "memory");
}
__device__ __forceinline__ void mbar_arrive(uint32_t bar) {
  asm volatile("mbarrier.arrive.shared::cta.b64 _, [%0];" ::"r"(bar) : "memory");
}
__device__ __forceinline__ void mbar_arrive_pred(uint32_t bar, bool p) {
  asm volatile("{ .reg .pred p; setp.ne.b32 p, %1, 0; @p mbarrier.arrive.shared::cta.b64 _, [%0]; }" ::"r"(bar), "r"((int)p) : "memory");
}
__device__ __forceinline__ void mbar_arrive_cl(uint32_t bar, uint32_t off, bool p = true) {
  asm volatile("{ .reg .pred p, q; .reg .b32 a; setp.ne.b32 q, %2, 0; setp.ne.and.b32 p, %0, 0, q; add.u32 a, %0, %1; @p mbarrier.arrive.shared::cluster.b64 _, [a]; }"
               ::"r"(bar), "r"(off), "r"((int)p) : "memory");
}
__device__ __forceinline__ uint32_t mapa(uint32_t addr, uint32_t cta) {
  uint32_t r; asm("mapa.shared::cluster.u32 %0, %1, %2;" : "=r"(r) : "r"(addr), "r"(cta)); return r;
}
__device__ __forceinline__ void cluster_arrive() { asm volatile("barrier.cluster.arrive.relaxed.aligned;" ::: "memory"); }
__device__ __forceinline__ void cluster_wait() { asm volatile("barrier.cluster.wait.aligned;" ::: "memory"); }
__device__ __forceinline__ void watchdog(uint32_t& n) {
}
__device__ __forceinline__ void mbar_wait(uint32_t bar, uint32_t parity) {
  asm volatile("{\n.reg .pred p;\nWAIT_%=:\nmbarrier.try_wait.parity.shared::cta.b64 p, [%0], %1;\n@!p bra WAIT_%=;\n}" ::"r"(bar), "r"(parity) : "memory");
}
__device__ __forceinline__ bool mbar_test(uint32_t bar, uint32_t parity) {
  uint32_t ok;
  asm volatile("{\n.reg .pred p;\nmbarrier.test_wait.parity.shared::cta.b64 p, [%1], %2;\nselp.u32 %0, 1, 0, p;\n}" : "=r"(ok) : "r"(bar), "r"(parity) : "memory");
  return ok;
}
__device__ __forceinline__ uint64_t l2_stream() {
  uint64_t f; asm("createpolicy.fractional.L2::evict_first.b64 %0, 1.0;" : "=l"(f)); return f;
}
__device__ __forceinline__ void tma2d(uint32_t dst, const CUtensorMap* m, int c0, int c1, uint32_t bar) {
  asm volatile("cp.async.bulk.tensor.2d.shared::cluster.global.mbarrier::complete_tx::bytes.L2::cache_hint [%0], [%1, {%3, %4}], [%2], %5;"
               ::"r"(dst), "l"(m), "r"(bar), "r"(c0), "r"(c1), "l"(l2_stream()) : "memory");
}
__device__ __forceinline__ void bulk_load(uint32_t dst, const void* src, uint32_t bytes, uint32_t bar) {
  asm volatile("cp.async.bulk.shared::cluster.global.mbarrier::complete_tx::bytes [%0], [%1], %2, [%3];" ::"r"(dst), "l"(src), "r"(bytes), "r"(bar) : "memory");
}
__device__ __forceinline__ void bulk_load_stream(uint32_t dst, const void* src, uint32_t bytes, uint32_t bar) {
  asm volatile("cp.async.bulk.shared::cluster.global.mbarrier::complete_tx::bytes.L2::cache_hint [%0], [%1], %2, [%3], %4;"
               ::"r"(dst), "l"(src), "r"(bytes), "r"(bar), "l"(l2_stream()) : "memory");
}
__device__ __forceinline__ void tma2d_store(const CUtensorMap* m, uint32_t src, int c0, int c1) {
  asm volatile("cp.async.bulk.tensor.2d.global.shared::cta.bulk_group [%0, {%2, %3}], [%1];" ::"l"(m), "r"(src), "r"(c0), "r"(c1) : "memory");
}
__device__ __forceinline__ void bulk_store(void* dst, uint32_t src, uint32_t bytes) {
  asm volatile("cp.async.bulk.global.shared::cta.bulk_group [%0], [%1], %2;" ::"l"(dst), "r"(src), "r"(bytes) : "memory");
}
__device__ __forceinline__ uint32_t unit_of(uint32_t table, uint32_t i) { return ((table >> (i * 4)) & 15) * UNIT; }
__device__ __forceinline__ void tma3d(uint32_t dst, const CUtensorMap* m, int c0, int c1, int c2, uint32_t bar) {
  asm volatile("cp.async.bulk.tensor.3d.shared::cluster.global.mbarrier::complete_tx::bytes.L2::cache_hint [%0], [%1, {%3, %4, %5}], [%2], %6;"
               ::"r"(dst), "l"(m), "r"(bar), "r"(c0), "r"(c1), "r"(c2), "l"(l2_stream()) : "memory");
}
template <bool STREAM>
__device__ __forceinline__ void tma3d_mc(uint32_t dst, const CUtensorMap* m, int c0, int c1, int c2, uint32_t bar) {
  if (STREAM)
    asm volatile("cp.async.bulk.tensor.3d.shared::cluster.global.mbarrier::complete_tx::bytes.multicast::cluster.L2::cache_hint [%0], [%1, {%3, %4, %5}], [%2], %6, %7;"
                 ::"r"(dst), "l"(m), "r"(bar), "r"(c0), "r"(c1), "r"(c2), "h"((uint16_t)3), "l"(l2_stream()) : "memory");
  else
    asm volatile("cp.async.bulk.tensor.3d.shared::cluster.global.mbarrier::complete_tx::bytes.multicast::cluster [%0], [%1, {%3, %4, %5}], [%2], %6;"
                 ::"r"(dst), "l"(m), "r"(bar), "r"(c0), "r"(c1), "r"(c2), "h"((uint16_t)3) : "memory");
}
__device__ __forceinline__ void prefetch_map(const CUtensorMap* m) {
  asm volatile("prefetch.tensormap [%0];" ::"l"(m) : "memory");
}
__device__ __forceinline__ void fence_async() { asm volatile("fence.proxy.async.global;" ::: "memory"); }
__device__ __forceinline__ void fence_async_smem() { asm volatile("fence.proxy.async.shared::cta;" ::: "memory"); }
__device__ __forceinline__ void bar_sync(int id, int n) { asm volatile("bar.sync %0, %1;" ::"r"(id), "r"(n) : "memory"); }
__device__ __forceinline__ void bar_arrive(int id, int n) { asm volatile("bar.arrive %0, %1;" ::"r"(id), "r"(n) : "memory"); }
__device__ __forceinline__ void wg_fence() { asm volatile("wgmma.fence.sync.aligned;" ::: "memory"); }
__device__ __forceinline__ void wg_commit() { asm volatile("wgmma.commit_group.sync.aligned;" ::: "memory"); }
template <int N> __device__ __forceinline__ void wg_wait() { asm volatile("wgmma.wait_group.sync.aligned %0;" ::"n"(N) : "memory"); }
__device__ __forceinline__ uint64_t make_desc(uint32_t addr, uint32_t lbo, uint32_t sbo) {
  return (uint64_t)((addr & 0x3FFFF) >> 4) | ((uint64_t)(lbo >> 4) << 16) | ((uint64_t)(sbo >> 4) << 32) | (1ull << 62);
}
__device__ __forceinline__ uint32_t ld_relaxed(const uint32_t* p) {
  uint32_t v; asm volatile("ld.relaxed.gpu.global.u32 %0, [%1];" : "=r"(v) : "l"(p) : "memory"); return v;
}
__device__ __forceinline__ uint32_t ld_acquire(const uint32_t* p) {
  uint32_t v; asm volatile("ld.acquire.gpu.global.u32 %0, [%1];" : "=r"(v) : "l"(p) : "memory"); return v;
}
__device__ __forceinline__ uint4 ld_relaxed4(const uint32_t* p) {
  uint4 v; asm volatile("ld.relaxed.gpu.global.v4.u32 {%0,%1,%2,%3}, [%4];" : "=r"(v.x), "=r"(v.y), "=r"(v.z), "=r"(v.w) : "l"(p) : "memory"); return v;
}
__device__ __forceinline__ uint2 ld_relaxed2(const uint32_t* p) {
  uint2 v; asm volatile("ld.relaxed.gpu.global.v2.u32 {%0,%1}, [%2];" : "=r"(v.x), "=r"(v.y) : "l"(p) : "memory"); return v;
}
__device__ __forceinline__ void st_relaxed(uint32_t* p, uint32_t v) {
  asm volatile("st.relaxed.gpu.global.u32 [%0], %1;" ::"l"(p), "r"(v) : "memory");
}
__device__ __forceinline__ void st_relaxed2(uint32_t* p, uint32_t a, uint32_t b) {
  asm volatile("st.relaxed.gpu.global.v2.u32 [%0], {%1,%2};" ::"l"(p), "r"(a), "r"(b) : "memory");
}
__device__ __forceinline__ void st_relaxed4(uint32_t* p, uint32_t a, uint32_t b, uint32_t c, uint32_t d) {
  asm volatile("st.relaxed.gpu.global.v4.u32 [%0], {%1,%2,%3,%4};" ::"l"(p), "r"(a), "r"(b), "r"(c), "r"(d) : "memory");
}
__device__ __forceinline__ void st_b128(uint32_t* p, uint32_t a, uint32_t b, uint32_t c, uint32_t d) {
  asm volatile("{ .reg .b64 u, v; .reg .b128 w; mov.b64 u, {%1, %2}; mov.b64 v, {%3, %4}; mov.b128 w, {u, v}; st.relaxed.gpu.global.b128 [%0], w; }"
               ::"l"(p), "r"(a), "r"(b), "r"(c), "r"(d) : "memory");
}
__device__ __forceinline__ uint4 ld_b128(const uint32_t* p) {
  uint4 r;
  asm volatile("{ .reg .b64 u, v; .reg .b128 w; ld.relaxed.gpu.global.b128 w, [%4]; mov.b128 {u, v}, w; mov.b64 {%0, %1}, u; mov.b64 {%2, %3}, v; }"
               : "=r"(r.x), "=r"(r.y), "=r"(r.z), "=r"(r.w) : "l"(p) : "memory");
  return r;
}
__device__ __forceinline__ void st_pairs(uint32_t* p, uint32_t a, uint32_t b, uint32_t tag) {
  asm volatile("{ .reg .b64 u, v; mov.b64 u, {%1, %3}; mov.b64 v, {%2, %3}; st.relaxed.gpu.global.v2.b64 [%0], {u, v}; }"
               ::"l"(p), "r"(a), "r"(b), "r"(tag) : "memory");
}
__device__ __forceinline__ uint4 ld_pairs(const uint32_t* p) {
  uint4 v;
  asm volatile("{ .reg .b64 u, v; ld.relaxed.gpu.global.v2.b64 {u, v}, [%4]; mov.b64 {%0, %1}, u; mov.b64 {%2, %3}, v; }"
               : "=r"(v.x), "=r"(v.y), "=r"(v.z), "=r"(v.w) : "l"(p) : "memory");
  return v;
}
__device__ __forceinline__ uint2 ld_pair(const uint32_t* p) {
  uint2 v;
  asm volatile("{ .reg .b64 u; ld.relaxed.gpu.global.b64 u, [%2]; mov.b64 {%0, %1}, u; }" : "=r"(v.x), "=r"(v.y) : "l"(p) : "memory");
  return v;
}
__device__ __forceinline__ void red_release(uint32_t* p, uint32_t v) {
  asm volatile("red.release.gpu.global.add.u32 [%0], %1;" ::"l"(p), "r"(v) : "memory");
}
__device__ __forceinline__ uint32_t ldg_nc1(const void* p) {
  uint32_t v;
  asm volatile("ld.global.nc.u32 %0, [%1];" : "=r"(v) : "l"(p));
  return v;
}
__device__ __forceinline__ uint4 ldg_nc4(const void* p) {
  uint4 v; asm volatile("ld.global.nc.L1::no_allocate.v4.u32 {%0,%1,%2,%3}, [%4];" : "=r"(v.x), "=r"(v.y), "=r"(v.z), "=r"(v.w) : "l"(p)); return v;
}
__device__ __forceinline__ uint4 ldg_stream4(const void* p) {
  uint4 v;
  asm volatile("ld.global.nc.L1::no_allocate.L2::cache_hint.v4.u32 {%0,%1,%2,%3}, [%4], %5;" : "=r"(v.x), "=r"(v.y), "=r"(v.z), "=r"(v.w) : "l"(p), "l"(l2_stream()));
  return v;
}
__device__ __forceinline__ void stg4(void* p, uint4 v) {
  asm volatile("st.global.v4.u32 [%0], {%1,%2,%3,%4};" ::"l"(p), "r"(v.x), "r"(v.y), "r"(v.z), "r"(v.w) : "memory");
}
__device__ __forceinline__ void wait_counter(const uint32_t* p, uint32_t target) {
  uint32_t n = 0;
  while (__any_sync(0xffffffffu, (int)(ld_acquire(p) - target) < 0)) { watchdog(n); }
}
__device__ __forceinline__ uint32_t tagf(float v, uint32_t tag) { return (__float_as_uint(v) & ~3u) | tag; }
__device__ __forceinline__ bool tag_ok(uint4 v, uint32_t tag) { return (((v.x ^ tag) | (v.y ^ tag) | (v.z ^ tag) | (v.w ^ tag)) & 3u) == 0; }
__device__ __forceinline__ float untag_sum(uint32_t a, uint32_t b) { return __uint_as_float(a & ~3u) + __uint_as_float(b & ~3u); }
__device__ __forceinline__ uint4 poll4(const uint32_t* p, uint32_t tag) {
  uint4 v = ld_relaxed4(p);
  uint32_t n = 0;
  while (!__all_sync(0xffffffffu, tag_ok(v, tag))) { v = ld_relaxed4(p); watchdog(n); }
  return v;
}
__device__ __forceinline__ float bf_lo(uint32_t v) { return __uint_as_float(v << 16); }
__device__ __forceinline__ float bf_hi(uint32_t v) { return __uint_as_float(v & 0xffff0000u); }
__device__ __forceinline__ uint32_t pack_bf(float lo, float hi) {
  uint32_t r; asm("cvt.rn.bf16x2.f32 %0, %1, %2;" : "=r"(r) : "f"(hi), "f"(lo)); return r;
}
__device__ __forceinline__ float rbf(float v) { return __uint_as_float(pack_bf(0.f, v) & 0xffff0000u); }
__device__ __forceinline__ uint32_t hmul2(uint32_t a, uint32_t b) {
  uint32_t r; asm("mul.rn.bf16x2 %0, %1, %2;" : "=r"(r) : "r"(a), "r"(b)); return r;
}
__device__ __forceinline__ uint32_t hadd2(uint32_t a, uint32_t b) {
  uint32_t r; asm("add.rn.bf16x2 %0, %1, %2;" : "=r"(r) : "r"(a), "r"(b)); return r;
}
__device__ __forceinline__ uint32_t hsub2(uint32_t a, uint32_t b) {
  uint32_t r; asm("sub.rn.bf16x2 %0, %1, %2;" : "=r"(r) : "r"(a), "r"(b)); return r;
}
__device__ __forceinline__ uint32_t hmax2(uint32_t a, uint32_t b) {
  uint32_t r; asm("max.bf16x2 %0, %1, %2;" : "=r"(r) : "r"(a), "r"(b)); return r;
}
__device__ __forceinline__ float rcp(float x) { float r; asm("rcp.approx.ftz.f32 %0, %1;" : "=f"(r) : "f"(x)); return r; }
__device__ __forceinline__ float ex2(float x) { float r; asm("ex2.approx.ftz.f32 %0, %1;" : "=f"(r) : "f"(x)); return r; }
__device__ __forceinline__ void stmatrix4(uint32_t addr, uint32_t a, uint32_t b, uint32_t c, uint32_t d) {
  asm volatile("stmatrix.sync.aligned.m8n8.x4.shared.b16 [%0], {%1,%2,%3,%4};" ::"r"(addr), "r"(a), "r"(b), "r"(c), "r"(d) : "memory");
}
__device__ __forceinline__ void ldmatrix4(uint32_t addr, uint32_t& a, uint32_t& b, uint32_t& c, uint32_t& d) {
  asm volatile("ldmatrix.sync.aligned.m8n8.x4.shared.b16 {%0,%1,%2,%3}, [%4];" : "=r"(a), "=r"(b), "=r"(c), "=r"(d) : "r"(addr) : "memory");
}
__device__ __forceinline__ void ldmatrix4t(uint32_t addr, uint32_t& a, uint32_t& b, uint32_t& c, uint32_t& d) {
  asm volatile("ldmatrix.sync.aligned.m8n8.x4.trans.shared.b16 {%0,%1,%2,%3}, [%4];" : "=r"(a), "=r"(b), "=r"(c), "=r"(d) : "r"(addr) : "memory");
}
__device__ __forceinline__ void mma16816(float (&d)[4], uint32_t a0, uint32_t a1, uint32_t a2, uint32_t a3, uint32_t b0, uint32_t b1) {
  asm volatile("mma.sync.aligned.m16n8k16.row.col.f32.bf16.bf16.f32 {%0,%1,%2,%3}, {%4,%5,%6,%7}, {%8,%9}, {%0,%1,%2,%3};"
               : "+f"(d[0]), "+f"(d[1]), "+f"(d[2]), "+f"(d[3]) : "r"(a0), "r"(a1), "r"(a2), "r"(a3), "r"(b0), "r"(b1));
}
__device__ __forceinline__ void sts1(uint32_t a, uint32_t v) { asm volatile("st.shared.u32 [%0], %1;" ::"r"(a), "r"(v) : "memory"); }
__device__ __forceinline__ uint4 lds4(uint32_t a) {
  uint4 v; asm volatile("ld.shared.v4.u32 {%0,%1,%2,%3}, [%4];" : "=r"(v.x), "=r"(v.y), "=r"(v.z), "=r"(v.w) : "r"(a) : "memory"); return v;
}
__device__ __forceinline__ uint2 lds2(uint32_t a) {
  uint2 v; asm volatile("ld.shared.v2.u32 {%0,%1}, [%2];" : "=r"(v.x), "=r"(v.y) : "r"(a) : "memory"); return v;
}
__device__ __forceinline__ uint32_t lds1(uint32_t a) {
  uint32_t v; asm volatile("ld.shared.u32 %0, [%1];" : "=r"(v) : "r"(a) : "memory"); return v;
}
__device__ __forceinline__ void sts2(uint32_t a, uint32_t x, uint32_t y) { asm volatile("st.shared.v2.u32 [%0], {%1,%2};" ::"r"(a), "r"(x), "r"(y) : "memory"); }
__device__ __forceinline__ void sts4(uint32_t a, uint4 v) {
  asm volatile("st.shared.v4.u32 [%0], {%1,%2,%3,%4};" ::"r"(a), "r"(v.x), "r"(v.y), "r"(v.z), "r"(v.w) : "memory");
}
__device__ __forceinline__ float silu_f(float v) { return __fdividef(v, 1.f + __expf(-v)); }
__device__ __forceinline__ uint32_t hfma2(uint32_t a, uint32_t b, uint32_t c) {
  uint32_t r; asm("fma.rn.bf16x2 %0, %1, %2, %3;" : "=r"(r) : "r"(a), "r"(b), "r"(c)); return r;
}
__device__ __forceinline__ void split_inv(float sd, uint32_t& ih, uint32_t& il) {
  const float inv = rcp(sd);
  ih = pack_bf(inv, inv);
  const float lo = inv - bf_lo(ih);
  il = pack_bf(lo, lo);
}
__device__ __forceinline__ uint32_t ln_norm(uint32_t x, uint32_t mean2, uint32_t ih, uint32_t il) {
  const uint32_t d = hsub2(x, mean2);
  return hfma2(d, ih, hmul2(d, il));
}
__device__ __forceinline__ uint32_t modul(uint32_t n, uint32_t c1, uint32_t sh) { return hadd2(hmul2(n, c1), sh); }
__device__ __forceinline__ uint32_t ln_mod(uint32_t x, uint32_t mean2, uint32_t ih, uint32_t il, uint32_t c1, uint32_t sh) {
  return modul(ln_norm(x, mean2, ih, il), c1, sh);
}

#define R8(a, i) "+f"(a[i]), "+f"(a[i + 1]), "+f"(a[i + 2]), "+f"(a[i + 3]), "+f"(a[i + 4]), "+f"(a[i + 5]), "+f"(a[i + 6]), "+f"(a[i + 7])
#define D64 "{%0,%1,%2,%3,%4,%5,%6,%7,%8,%9,%10,%11,%12,%13,%14,%15,%16,%17,%18,%19,%20,%21,%22,%23,%24,%25,%26,%27,%28,%29,%30,%31," \
            "%32,%33,%34,%35,%36,%37,%38,%39,%40,%41,%42,%43,%44,%45,%46,%47,%48,%49,%50,%51,%52,%53,%54,%55,%56,%57,%58,%59,%60,%61,%62,%63}"
template <int TB>
__device__ __forceinline__ void mma_ss(float (&d)[64], uint64_t da, uint64_t db, int sc) {
  asm volatile("{\n.reg .pred p;\nsetp.ne.b32 p, %66, 0;\n"
               "wgmma.mma_async.sync.aligned.m64n128k16.f32.bf16.bf16 " D64 ", %64, %65, p, 1, 1, 0, %67;\n}"
               : R8(d, 0), R8(d, 8), R8(d, 16), R8(d, 24), R8(d, 32), R8(d, 40), R8(d, 48), R8(d, 56)
               : "l"(da), "l"(db), "r"(sc), "n"(TB));
}
template <int TB>
__device__ __forceinline__ void mma_rs(float (&d)[64], uint32_t a0, uint32_t a1, uint32_t a2, uint32_t a3, uint64_t db, int sc) {
  asm volatile("{\n.reg .pred p;\nsetp.ne.b32 p, %69, 0;\n"
               "wgmma.mma_async.sync.aligned.m64n128k16.f32.bf16.bf16 " D64 ", {%64,%65,%66,%67}, %68, p, 1, 1, %70;\n}"
               : R8(d, 0), R8(d, 8), R8(d, 16), R8(d, 24), R8(d, 32), R8(d, 40), R8(d, 48), R8(d, 56)
               : "r"(a0), "r"(a1), "r"(a2), "r"(a3), "l"(db), "r"(sc), "n"(TB));
}
#define D128 "{%0,%1,%2,%3,%4,%5,%6,%7,%8,%9,%10,%11,%12,%13,%14,%15,%16,%17,%18,%19,%20,%21,%22,%23,%24,%25,%26,%27,%28,%29,%30,%31," \
             "%32,%33,%34,%35,%36,%37,%38,%39,%40,%41,%42,%43,%44,%45,%46,%47,%48,%49,%50,%51,%52,%53,%54,%55,%56,%57,%58,%59,%60,%61,%62,%63," \
             "%64,%65,%66,%67,%68,%69,%70,%71,%72,%73,%74,%75,%76,%77,%78,%79,%80,%81,%82,%83,%84,%85,%86,%87,%88,%89,%90,%91,%92,%93,%94,%95," \
             "%96,%97,%98,%99,%100,%101,%102,%103,%104,%105,%106,%107,%108,%109,%110,%111,%112,%113,%114,%115,%116,%117,%118,%119,%120,%121,%122,%123,%124,%125,%126,%127}"
#define R128(d, e) R8(d, 0), R8(d, 8), R8(d, 16), R8(d, 24), R8(d, 32), R8(d, 40), R8(d, 48), R8(d, 56), \
                   R8(e, 0), R8(e, 8), R8(e, 16), R8(e, 24), R8(e, 32), R8(e, 40), R8(e, 48), R8(e, 56)
__device__ __forceinline__ void mma256_ss(float (&d)[64], float (&e)[64], uint64_t da, uint64_t db, int sc) {
  asm volatile("{\n.reg .pred p;\nsetp.ne.b32 p, %130, 0;\n"
               "wgmma.mma_async.sync.aligned.m64n256k16.f32.bf16.bf16 " D128 ", %128, %129, p, 1, 1, 0, 1;\n}"
               : R128(d, e) : "l"(da), "l"(db), "r"(sc));
}
__device__ __forceinline__ void mma256_rs(float (&d)[64], float (&e)[64], uint32_t a0, uint32_t a1, uint32_t a2, uint32_t a3, uint64_t db) {
  asm volatile("{\n.reg .pred p;\nsetp.ne.b32 p, 1, 0;\n"
               "wgmma.mma_async.sync.aligned.m64n256k16.f32.bf16.bf16 " D128 ", {%128,%129,%130,%131}, %132, p, 1, 1, 1;\n}"
               : R128(d, e) : "r"(a0), "r"(a1), "r"(a2), "r"(a3), "l"(db));
}
template <int N> __device__ __forceinline__ void keep(float (&a)[N]) {
#pragma unroll
  for (int i = 0; i < N; i++) asm volatile("" : "+f"(a[i])::"memory");
}
template <int N> __device__ __forceinline__ void keep(uint32_t (&a)[N]) {
#pragma unroll
  for (int i = 0; i < N; i++) asm volatile("" : "+r"(a[i])::"memory");
}

#define STAMP(idx) do {} while (0)
#define PROF(grp, cond, idx) do {} while (0)

constexpr float SCL2 = 1.4426950408889634f * 0.08838834764831845f;

__device__ __forceinline__ void pack_p(const float (&s)[64], uint32_t (&p)[32]) {
#pragma unroll
  for (int i = 0; i < 32; i++) p[i] = pack_bf(s[2 * i], s[2 * i + 1]);
}

__device__ __forceinline__ void issue_qk(float (&s)[64], uint32_t q0, uint32_t q1, uint32_t kslot) {
  const uint64_t db = make_desc(kslot, 16, 1024), da0 = make_desc(q0, 16, 1024), da1 = make_desc(q1, 16, 1024);
#pragma unroll
  for (int kk = 0; kk < 8; kk++) mma_ss<0>(s, (kk < 4 ? da0 : da1) + (kk & 3) * 2, db + (kk >> 2) * 1024 + (kk & 3) * 2, kk != 0);
}
__device__ __forceinline__ void issue_pv(float (&o)[64], uint32_t (&p)[32], uint32_t vslot, int acc) {
  uint64_t db = make_desc(vslot, 16384, 1024);
#pragma unroll
  for (int kk = 0; kk < 8; kk++)
    mma_rs<1>(o, p[4 * kk], p[4 * kk + 1], p[4 * kk + 2], p[4 * kk + 3], db + kk * 128, kk == 0 ? acc : 1);
}

template <int H>
__device__ __forceinline__ void store_chunk(const float (&a)[64], uint32_t addr) {
#pragma unroll
  for (int i = 8 * H; i < 8 * H + 8; i += 2)
    stmatrix4(addr ^ ((i & 7) << 4), pack_bf(a[4 * i], a[4 * i + 1]), pack_bf(a[4 * i + 2], a[4 * i + 3]),
              pack_bf(a[4 * i + 4], a[4 * i + 5]), pack_bf(a[4 * i + 6], a[4 * i + 7]));
}
template <int H>
__device__ __forceinline__ void store_chunk(const float (&a)[64], float i0, float i1, uint32_t addr) {
#pragma unroll
  for (int i = 8 * H; i < 8 * H + 8; i += 2)
    stmatrix4(addr ^ ((i & 7) << 4), pack_bf(a[4 * i] * i0, a[4 * i + 1] * i0), pack_bf(a[4 * i + 2] * i1, a[4 * i + 3] * i1),
              pack_bf(a[4 * i + 4] * i0, a[4 * i + 5] * i0), pack_bf(a[4 * i + 6] * i1, a[4 * i + 7] * i1));
}
__device__ __forceinline__ float inv_quad_sum(float l) {
  l += __shfl_xor_sync(0xffffffffu, l, 1);
  l += __shfl_xor_sync(0xffffffffu, l, 2);
  return rcp(l);
}

__device__ __forceinline__ void ln_scalars(float mean, float var, float& mb, float& sd) {
  mb = rbf(mean);
  float r; asm("sqrt.approx.ftz.f32 %0, %1;" : "=f"(r) : "f"(rbf(rbf(var) + 1e-5f)));
  sd = rbf(r);
}

__global__ void __cluster_dims__(2, 1, 1) __launch_bounds__(384, 1) fused_kernel(const __grid_constant__ Maps maps, const Ptrs P) {
  extern __shared__ __align__(1024) uint8_t smem_raw[];
  const uint32_t base = smem_u32(smem_raw);
  const int tid = threadIdx.x, lane = tid & 31;
  const int warp = __shfl_sync(0xffffffffu, tid >> 5, 0);
  const int b = blockIdx.x;
  PROF(31, tid == 0, 0);

  if (b >= NMAIN) {
    float* sc = reinterpret_cast<float*>(smem_raw);
    float* red = sc + DM;
    for (int k = tid; k < DM; k += 384) sc[k] = rbf(silu_f(__bfloat162float(P.c[k])));
    __syncthreads();
    if (tid < 256) {
      const int col = 2048 + (b - NMAIN) * 1024 + (tid & 127) * 8, r0 = (tid >> 7) * 512;
      float acc[8];
#pragma unroll
      for (int e = 0; e < 8; e++) acc[e] = 0.f;
#pragma unroll 1
      for (int r = r0; r < r0 + 512; r += HU) {
        uint4 w[HU];
#pragma unroll
        for (int u = 0; u < HU; u++) w[u] = ldg_stream4(P.w_mod + (size_t)(r + u) * NMOD + col);
#pragma unroll
        for (int u = 0; u < HU; u++) {
          float s = sc[r + u];
          acc[0] += s * bf_lo(w[u].x); acc[1] += s * bf_hi(w[u].x); acc[2] += s * bf_lo(w[u].y); acc[3] += s * bf_hi(w[u].y);
          acc[4] += s * bf_lo(w[u].z); acc[5] += s * bf_hi(w[u].z); acc[6] += s * bf_lo(w[u].w); acc[7] += s * bf_hi(w[u].w);
        }
      }
      if (tid >= 128) {
#pragma unroll
        for (int e = 0; e < 8; e++) red[(tid & 127) * 8 + e] = acc[e];
      }
      const uint32_t tag = ld_relaxed(&g_epoch) % 3 + 1;
      bar_sync(1, 256);
      if (tid < 128) {
        uint32_t o[8];
#pragma unroll
        for (int e = 0; e < 8; e++) o[e] = __float_as_uint(rbf(acc[e] + red[tid * 8 + e])) | tag;
        st_relaxed4(g_mod + col, o[0], o[1], o[2], o[3]);
        st_relaxed4(g_mod + col + 4, o[4], o[5], o[6], o[7]);
        const uint4 wr = ldg_nc4(P.w_r + tid * 8);
        const uint32_t wv[4] = {wr.x, wr.y, wr.z, wr.w};
        float dsum = 0.f;
#pragma unroll
        for (int e = 0; e < 8; e++) {
          const float m = bf_hi(o[e]);
          dsum += (b == NMAIN + 2 ? rbf(1.f + m) : m) * ((e & 1) ? bf_hi(wv[e >> 1]) : bf_lo(wv[e >> 1]));
        }
#pragma unroll
        for (int k = 16; k > 0; k >>= 1) dsum += __shfl_xor_sync(0xffffffffu, dsum, k);
        if (lane == 0) st_relaxed(g_mod + (b - NMAIN) * 4 + warp, tagf(dsum, tag));
      }
    }
    PROF(2, tid == 0, 1);
    return;
  }

  const int rank = b & 1;
  const int rb = ((b >> 4) << 1) | rank, cj = (b >> 1) & 7;
  const uint32_t bfull = base + OFF_BAR, bempty = bfull + NSLOT * 8;
  const uint32_t gfull = bempty + NSLOT * 8, gempty = gfull + 32;
  const uint32_t bar_ofull = gempty + 32;
  const uint32_t bar_ofree = bar_ofull + 32;
  const uint32_t bar_par = bar_ofree + 32;
  const uint32_t bar_mod = bar_par + 8;
  const uint32_t bar_pread = bar_mod + 8;
  const uint32_t bar_xres = bar_pread + 8;
  const uint32_t bar_ring = bar_xres + 8;
  const uint32_t bar_box = bar_ring + 24;
  const uint32_t bar_go = bar_box + 96;
  const uint32_t bar_go2 = bar_go + 16;
  const uint32_t bar_cnt = bar_go + 24;
  const uint32_t xfull = bar_go + 32, xempty = xfull + 32;
  const uint32_t bar_hw = xempty + 32, bar_hx = bar_hw + 8;
  const uint32_t bar_hpub = bar_hx + 16;
  const uint32_t bar_win = bar_hpub + 16;
  const uint32_t bar_rx = bar_win + 8;
  const uint32_t bar_sel = bar_rx + 8;
  const uint32_t bar_gate = bar_sel + 8;
  const uint32_t bar_rel = bar_gate + 8;
  const uint32_t bar_od = bar_rel + 8;
  const uint32_t bar_res = bar_go + 8;
  const uint32_t stage = base + OFF_STAGE, par = base + OFF_PAR;

  if (warp == 8 && elect_one()) {
    for (int s = 0; s < NSLOT; s++) { mbar_init(bfull + s * 8, 1); mbar_init(bempty + s * 8, 16); }
    for (int s = 0; s < 4; s++) { mbar_init(gfull + s * 8, 1); mbar_init(gempty + s * 8, 16); mbar_init(xfull + s * 8, 1); mbar_init(xempty + s * 8, 8); mbar_init(bar_ofree + s * 8, 1); mbar_init(bar_ofull + s * 8, 128); }
    mbar_init(bar_par, 64); mbar_init(bar_mod, 256); mbar_init(bar_pread, 2); mbar_init(bar_xres, 1);
    mbar_init(bar_ring, 8); mbar_init(bar_ring + 8, 8); mbar_init(bar_ring + 16, 8);
    mbar_init(bar_go, 1); mbar_init(bar_go2, 1); mbar_init(bar_cnt, 1); mbar_init(bar_hpub, 8); mbar_init(bar_hpub + 8, 8); mbar_init(bar_res, 1); mbar_init(bar_win, 1); mbar_init(bar_rx, 1); mbar_init(bar_sel, 64); mbar_init(bar_gate, 8); mbar_init(bar_rel, 8); mbar_init(bar_od, 1);
    for (int s = 0; s < 12; s++) mbar_init(bar_box + s * 8, 1);
    asm volatile("fence.mbarrier_init.release.cluster;" ::: "memory");
    prefetch_map(&maps.x); prefetch_map(&maps.wq); prefetch_map(&maps.k); prefetch_map(&maps.v);
  }
  if (warp == 9 && elect_one()) {
    mbar_init(bar_hw, 1); mbar_init(bar_hx, 1); mbar_init(bar_hx + 8, 1);
    asm volatile("fence.mbarrier_init.release.cluster;" ::: "memory");
    mbar_expect_tx(bar_hw, 32768);
    mbar_expect_tx(bar_hx, 16384);
    mbar_expect_tx(bar_hx + 8, 16384);
    const __nv_bfloat16* xs = P.x + (size_t)(rb * 128 + cj * 16) * DM;
    bulk_load(base + 2 * GST_BYTES, xs, 16384, bar_hx);
    tma2d(stage, &maps.wm, (b >> 1) * 32, rank * 512, bar_hw);
    tma2d(stage + 16384, &maps.wm, (b >> 1) * 32, rank * 512 + 256, bar_hw);
    bulk_load(base + 3 * GST_BYTES, xs + 8 * DM, 16384, bar_hx + 8);
  }
  cluster_arrive();

  if (warp >= 8) {
    asm volatile("setmaxnreg.dec.sync.aligned.u32 40;");
    if (warp < 10) bar_arrive(1, 320);
    const uint32_t epoch = ld_relaxed(&g_epoch);
    cluster_wait();
    if (warp == 8) {
      const int kvrow = (cj >> 1) * SK + (SK - WIN);
      int wch = cj * 8 + rank * 2;
#pragma unroll 1
      for (int ps = 0; ps < 3; ps++) {
        const CUtensorMap* mw = ps == 2 ? &maps.wo : &maps.wq;
        const uint32_t xt = ps == 1 ? XT1 : XT2, wt = ps == 0 ? WT0 : (ps == 1 ? WT1 : WT2);
        const int nst = ps == 2 ? 32 : 16;
#pragma unroll 1
        for (int i = 0; i < nst; i++) {
          const uint32_t bf = gfull + (i & 3) * 8;
          const int kt = ps == 2 ? (((cj & 1) * 4 + ((i >> 1) & 3)) * 4 + (i >> 3)) * 2 + (i & 1) : (i + (ps ? 0 : b & 14)) & 15;
          const uint32_t wd = base + unit_of(wt, i & 3) + rank * UNIT, xd = base + unit_of(xt, i & 3);
          const uint8_t* xs = g_act + (uint32_t)(rb * 80 + (ps - 1) * 16 + kt) * UNIT;
          if (ps == 0 && i == HD) mbar_wait(bar_mod, 0);
          const bool xfirst = ps && i < 2;
          if (ps == 2 && i == 0) mbar_wait(bar_ofree + 24, 0);
          if (i == 0) fence_async();
          mbar_wait(gempty + (i & 3) * 8, ((i >> 2) & 1) ^ 1);
          if (elect_one()) {
            mbar_expect_tx(bf, ps ? GST_BYTES : 2 * UNIT);
            if (xfirst) bulk_load_stream(xd, xs, UNIT, bf);
          }
          if (ps && i < 4) mbar_wait(bempty + i * 8, 1);
          if (elect_one()) tma3d_mc<true>(wd, mw, 0, (i == 31 ? kt ^ (rank * 32) : kt) * 64, i == 31 ? cj * 2 : wch, bf);
          if (ps) {
            if (i == 16) { mbar_wait(bar_cnt, 0); fence_async(); }
            if (i == 2) mbar_wait(bar_ofree + (ps - 1) * 16, 0);
            if (elect_one()) {
              if (i == 31) bulk_load(xd, xs, UNIT, bf); else if (!xfirst) bulk_load_stream(xd, xs, UNIT, bf);
              mbar_arrive_pred(bar_go, i == GOST - 1);
              mbar_arrive_pred(bar_od, i == ODS);
              mbar_arrive_pred(bar_res, ((1u << RES0 | 1u << RES1) >> i) & 1);
            }
          }
        }
        if (ps == 2) break;
        wch = ps ? ((wch >> 3) ^ rank) * 2 : wch + 4;
#pragma unroll 1
        for (int u = 0; u < 16; u++) {
          const bool isk = (u == 0) || ((u & 1) && u < 15);
          const int blk = (isk ? (u + 1) >> 1 : (u == 15 ? 7 : (u >> 1) - 1)) & 3;
          const uint32_t sl = base + unit_of(ps ? AT1 : AT0, u & 3) + rank * UNIT, bf = bfull + (u & 3) * 8;
          if (u < 4) mbar_wait(gempty + ((u + 1) >> 1) * 8, 1);
          mbar_wait(bempty + (u & 3) * 8, ((u >> 2) & 1) ^ 1);
          if (elect_one()) {
            mbar_arrive_pred(bar_go2, ps && u == PG0);
            mbar_expect_tx(bf, SLOT_BYTES);
            tma3d_mc<false>(sl, isk ? &maps.k : &maps.v, 0, kvrow + blk * 128, rank, bf);
          }
        }
      }
      if (elect_one()) mbar_expect_tx(bar_rx, UNIT);
      mbar_wait(bar_rel, 0);
      if (elect_one()) {
        bulk_load_stream(base + UNIT, g_act + (uint32_t)(rb * 80 + 16 + 63 - (cj & 1) * 32) * UNIT, UNIT, bar_rx);
      }
      if (b < NFFN) {
#pragma unroll 1
        for (int u = 0; u < 12; u++) {
          const uint32_t dst = base + unit_of(u < 4 ? FT_G : (u < 8 ? FT_U : FT_D), u & 3);
          if (elect_one()) mbar_expect_tx(bar_box + u * 8, UNIT);
          if (u == FB0 || u == 2 || u == FB2) mbar_wait(bar_ring + (u == FB2 ? 16 : (u + 6) & 8), 0);
          if (u >= FPACE) mbar_wait(bar_box + (u - FPACE) * 8, 0);
          if (elect_one()) {
            if (u < 8) tma2d(dst, u < 4 ? &maps.wg : &maps.wu, b * 32, (u & 3) * 256, bar_box + u * 8);
            else tma3d(dst, &maps.wd, 0, b * 32, (u - 8) * 4, bar_box + u * 8);
          }
        }
      }
    } else if (warp == 9) {
      const uint32_t target = 8 * (epoch + 1);
      uint32_t hmask = 0;
#pragma unroll 1
      for (int i = 0; i < 16; i++) {
        if (i == HDX) mbar_wait(bar_mod, 0);
        const uint32_t need = i == 15 ? 0xffffu : 1u << ((2 * cj + i) & 15);
        if (i >= NRS && (hmask & need) != need) {
          uint32_t n = 0;
          do { hmask = __ballot_sync(0xffffffffu, ld_acquire(&g_cnt_h[rb * 32 + (lane & 15)]) == epoch + 1); watchdog(n); } while ((hmask & need) != need);
          PROF(1, lane == 0 && i == NRS, 26);
          fence_async();
        }
        mbar_wait(xempty + (i & 3) * 8, ((i >> 2) & 1) ^ 1);
        if (elect_one()) {
          mbar_expect_tx(xfull + (i & 3) * 8, UNIT);
          if (i < NRS) tma2d(base + (i & 3) * GST_BYTES, &maps.x, ((2 * cj + i) & 15) * 64, rb * 128, xfull + (i & 3) * 8);
          else bulk_load_stream(base + (i & 3) * GST_BYTES, g_act + (uint32_t)(rb * 80 + ((2 * cj + i) & 15)) * UNIT, UNIT, xfull + (i & 3) * 8);
        }
      }
      prefetch_map(&maps.wo);
#pragma unroll 1
      for (int t = 0; t < 4; t++) {
        if (t & 1) mbar_wait(bar_od, t >> 1);
#pragma unroll 1
        for (int p = 0; p < 32768 / OPS; p++) {
          const uint32_t w = p / (16384 / OPS), c = (p / (8192 / OPS)) & 1, off = w * 8192 + (p % (8192 / OPS)) * OPS;
          mbar_wait(bar_ofull + (t & 1) * 16 + w * 8, t >> 1);
          if (elect_one()) {
            bulk_store(g_act + (uint32_t)(rb * 80 + 16 + (cj * 4 + t) * 2 + c) * UNIT + off, base + unit_of(QT, 2 * t + c) + off, OPS);
            asm volatile("cp.async.bulk.commit_group;" ::: "memory");
            asm volatile("cp.async.bulk.wait_group.read %0;" ::"n"(OFL) : "memory");
          }
        }
        if (elect_one()) {
          asm volatile("cp.async.bulk.wait_group.read 0;" ::: "memory");
          mbar_arrive_pred(bar_ofree + t * 8, t < 3);
          asm volatile("cp.async.bulk.wait_group 0;" ::: "memory");
          fence_async();
          red_release(&g_cnt_o[((rb * 4 + t) * 2 + (cj >> 2)) * 32], 2);
        }
        if (t & 1) {
          wait_counter(&g_cnt_o[(rb * 8 + 2 * t - 2 + (cj & 1)) * 32], target);
          wait_counter(&g_cnt_o[(rb * 8 + 2 * t + (cj & 1)) * 32], target);
          if (elect_one()) mbar_arrive_pred(bar_ofree + 24, t == 1);
        }
      }
      wait_counter(&g_cnt_o[(rb * 8 + 7 - (cj & 1)) * 32], target);
      fence_async();
      if (elect_one()) {
        mbar_arrive(bar_cnt);
        PROF(2, true, 27);
        mbar_expect_tx(bar_xres, 32768);
      }
#pragma unroll 1
      for (int u = 0; u < 2; u++) {
        mbar_wait(bar_res, u);
        if (elect_one()) tma2d(base + OFF_RES + u * UNIT, &maps.x, cj * 128 + u * 64, rb * 128, bar_xres);
      }
      const uint32_t tag = epoch % 3 + 1;
      const uint32_t* inbox = g_cand + (lane & 15);
      mbar_wait(bar_ring + 16, 0);
      uint32_t c0 = ld_relaxed(inbox), n = 0;
#define CAND_STEP(cv)                                                                                        \
      {                                                                                                      \
        const bool valid = (cv & 3u) == tag, all = __all_sync(0xffffffffu, valid);                           \
        const uint32_t best = __reduce_max_sync(0xffffffffu, valid ? cv : 0u);                               \
        const uint32_t blk = __ffs(__ballot_sync(0xffffffffu, cv == best)) - 1;                              \
        if (best) sts2(par + PAR_CONST + 56, best, (blk << 7 | (~best >> 2 & 127)) | (all ? 0x1800 : 0x800)); \
        if (all) break;                                                                                      \
        cv = ld_relaxed(inbox);                                                                              \
      }
      while (true) { CAND_STEP(c0) watchdog(n); }
    } else {
      const int t2 = tid - 320;
      mbar_wait(bar_hpub + (warp & 1) * 8, 0);
      PROF(1, t2 == 0, 24);
#pragma unroll 1
      for (int c = 0; c < 8; c++) {
        const uint32_t off = (warp & 1) * UNIT + c * 2048 + lane * 16;
        uint8_t* dst = g_act + (uint32_t)(rb * 80 + cj * 2) * UNIT + off;
        const uint4 v0 = lds4(stage + off), v1 = lds4(stage + off + 512), v2 = lds4(stage + off + 1024), v3 = lds4(stage + off + 1536);
        stg4(dst, v0); stg4(dst + 512, v1); stg4(dst + 1024, v2); stg4(dst + 1536, v3);
      }
      __syncwarp();
      PROF(1, t2 == 0, 15);
      if (lane == 0) {
        mbar_arrive(bar_pread);
        red_release(&g_cnt_h[rb * 32 + cj * 2 + (warp & 1)], 1);
        PROF(1, t2 == 0, 25);
        prefetch_map(&maps.wg); prefetch_map(&maps.wu); prefetch_map(&maps.wd); prefetch_map(&maps.out);
      }
      __syncwarp();
      if (b < NFFN) {
        mbar_wait(bar_go2, 0);
        const __nv_bfloat16* pg = ((b & 1) ? P.w_up : P.w_gate) + (b >> 1) * 64 + (size_t)t2 * FF;
        const __nv_bfloat16* pd = P.w_down + (size_t)b * 32768 + t2 * 64;
        PROF(2, t2 == 0, 13);
#pragma unroll 1
        for (int i = 0; i < WN; i += WB) {
          uint32_t v[WB];
#pragma unroll
          for (int u = 0; u < WB; u++) {
            const int k = i + u;
            asm volatile("ld.global.cg.L2::128B.u32 %0, [%1];" : "=r"(v[u]) : "l"(k < 16 ? pg + (size_t)k * 64 * FF : pd + (k - 16) * 4096));
          }
#pragma unroll
          for (int u = 1; u < WB; u++) v[0] ^= v[u];
          sts1(par + PAR_SINK + t2 * 4, v[0]);
        }
        PROF(2, t2 == 0, 14);
      }
      const uint32_t tag = epoch % 3 + 1;
      mbar_wait(bar_go, 0);
      if (warp == 10) {
        const uint32_t* src = g_mod + 2 * DM + cj * 128 + lane * 4;
        const uint2 wr = *reinterpret_cast<const uint2*>(P.w_r + cj * 128 + lane * 4);
        uint4 vga, vsb, vcb, vgb;
        uint32_t n = 0;
        do {
          vga = ld_relaxed4(src); vsb = ld_relaxed4(src + DM); vcb = ld_relaxed4(src + 2 * DM); vgb = ld_relaxed4(src + 3 * DM);
          watchdog(n);
        } while (!__all_sync(0xffffffffu, tag_ok(vga, tag) && tag_ok(vsb, tag) && tag_ok(vcb, tag) && tag_ok(vgb, tag)));
        const float c0 = rbf(1.f + bf_hi(vcb.x)), c1 = rbf(1.f + bf_hi(vcb.y)), c2 = rbf(1.f + bf_hi(vcb.z)), c3 = rbf(1.f + bf_hi(vcb.w));
        const float a0 = c0 * bf_lo(wr.x), a1 = c1 * bf_hi(wr.x), a2 = c2 * bf_lo(wr.y), a3 = c3 * bf_hi(wr.y);
        const uint32_t h0 = pack_bf(a0, a1), h1 = pack_bf(a2, a3);
        const uint32_t t1 = par + PAR_T1 + (lane >> 2) * 64 + (lane & 1) * 32 + (lane & 2) * 2;
        sts1(t1, h0); sts1(t1 + 8, pack_bf(a0 - bf_lo(h0), a1 - bf_hi(h0)));
        sts1(t1 + 16, h1); sts1(t1 + 24, pack_bf(a2 - bf_lo(h1), a3 - bf_hi(h1)));
        sts4(par + PAR_T2 + lane * 32, make_uint4(pack_bf(c0, c1), __byte_perm(vsb.x, vsb.y, 0x7632), __byte_perm(vgb.x, vgb.y, 0x7632), __byte_perm(vga.x, vga.y, 0x7632)));
        sts4(par + PAR_T2 + lane * 32 + 16, make_uint4(pack_bf(c2, c3), __byte_perm(vsb.z, vsb.w, 0x7632), __byte_perm(vgb.z, vgb.w, 0x7632), __byte_perm(vga.z, vga.w, 0x7632)));
      } else {
        const uint4 g = poll4((lane & 2) ? g_mod + 8 - (lane & 1) * 4 : g_mod + 5 * DM + b * 8 + (lane & 1) * 4, tag);
        sts1(par + PAR_CONST + 60, 0);
        if (lane < 2) sts4(par + PAR_CONST + 16 + lane * 16, g);
        else if (lane < 4) sts2(par + PAR_CONST + (lane - 2) * 8, __float_as_uint(untag_sum(g.x, g.y) + untag_sum(g.z, g.w)), epoch);
      }
      __syncwarp();
#pragma unroll 4
      for (int q = XR; q < XE; q++) st_b128(g_xch + ((size_t)b * 8 * 256 + q * 64 + t2) * 4, (epoch & 1) << 16, 0, 0, 0);
      for (int q = 0; q < 2; q++) st_relaxed4(g_stats + ((size_t)cj * SEQ + rb * 128 + q * 64 + t2) * 4, 0, 0, 0, 0);
      if (b < NFFN)
        for (int q = 0; q < 4; q++) st_relaxed4(g_ypart + ((size_t)(q * 32 + (t2 >> 1)) * NFFN + b) * 8 + (t2 & 1) * 4, 0, 0, 0, 0);
      st_relaxed4(g_row + rb * 2 * DM + (t2 >> 5) * DM + cj * 128 + (t2 & 31) * 4, 0, 0, 0, 0);
      __threadfence();
      mbar_arrive(bar_par);
      mbar_wait(bar_gate, 0);
      uint32_t have = 0, n = 0;
      while (true) {
        const uint32_t st = lds1(par + PAR_CONST + 60) >> 7;
        if ((st & 31) != have) {
          const uint32_t* hsrc = g_row + (st & 15) * 2 * DM + t2 * 4;
          uint4 hv[4];
          bool ok = true;
#pragma unroll
          for (int i = 0; i < 4; i++) hv[i] = ld_pairs(hsrc + i * 256);
#pragma unroll
          for (int i = 0; i < 4; i++) {
            sts2(base + ((FT_G >> i * 4) & 15) * UNIT + (warp & 1) * 8192 + 256 + lane * 8, hv[i].x, hv[i].z);
            ok = ok && hv[i].y == tag && hv[i].w == tag;
          }
          have = __all_sync(0xffffffffu, ok) ? st & 31 : 0;
        }
        if ((st ^ have) == 32) break;
        watchdog(n);
      }
      mbar_arrive(bar_sel);
    }
    __syncwarp();
    cluster_arrive();
    {
      const uint32_t tag = epoch % 3 + 1, t3 = tid - 256;
      mbar_wait(bar_win, 0);
      uint2 win = lds2(par + PAR_CONST + 56);
      win.y &= 0x7ff;
      const uint32_t* fsrc = g_row + (win.y >> 7) * 2 * DM + (b >> 1) * 16 + (t3 & 3) * 4 + (b & 1) * 2;
      const uint32_t* ysrc = g_ypart + (size_t)b * NFFN * 8 + min(t3, NFFN - 1) * 4;
      uint2 fh = ld_pair(fsrc), fx = ld_pair(fsrc + DM);
      if (PSL) __nanosleep(PSL);
      uint4 ya = ld_relaxed4(ysrc), yb = ld_relaxed4(ysrc + NFFN * 4);
      const float rwin = __uint_as_float(((int)win.x < 0 ? win.x & 0x7fffffffu : ~win.x) & ~0x1ffu);
      const float rs = rbf(rcp(1.f + __expf(-rbf(rwin))));
      uint32_t n = 0;
      while (__any_sync(0xffffffffu, fh.y != tag || fx.y != tag)) { fh = ld_pair(fsrc); fx = ld_pair(fsrc + DM); watchdog(n); }
      while (!__all_sync(0xffffffffu, tag_ok(ya, tag) && tag_ok(yb, tag))) {
        if (!tag_ok(ya, tag)) ya = ld_relaxed4(ysrc);
        if (!tag_ok(yb, tag)) yb = ld_relaxed4(ysrc + NFFN * 4);
        watchdog(n);
      }
      __syncwarp();
      PROF(8, t3 == 0, 5);
      float y0 = untag_sum(ya.x, yb.x), y1 = untag_sum(ya.y, yb.y), y2 = untag_sum(ya.z, yb.z), y3 = untag_sum(ya.w, yb.w);
      const bool u1 = lane & 2, u2 = lane & 4;
      y0 = (u1 ? y2 : y0) + __shfl_xor_sync(0xffffffffu, u1 ? y0 : y2, 2);
      y1 = (u1 ? y3 : y1) + __shfl_xor_sync(0xffffffffu, u1 ? y1 : y3, 2);
      y0 = (u2 ? y1 : y0) + __shfl_xor_sync(0xffffffffu, u2 ? y0 : y1, 4);
      y0 += __shfl_xor_sync(0xffffffffu, y0, 8);
      if (!(lane & 8)) sts1(par + PAR_RED + 64 + (t3 >> 4) * 32 + ((lane & 1) * 4 + (lane & 2) + ((lane >> 2) & 1)) * 4, __float_as_uint(y0));
      bar_sync(4, 128);
      if (t3 < 4) {
        y0 = 0.f; y1 = 0.f;
#pragma unroll
        for (int w4 = 0; w4 < 7; w4++) {
          const uint2 v = lds2(par + PAR_RED + 64 + w4 * 32 + t3 * 8);
          y0 += __uint_as_float(v.x); y1 += __uint_as_float(v.y);
        }
        const uint2 gv = lds2(par + PAR_CONST + 16 + t3 * 8);
        const uint32_t upd = hmul2(pack_bf(y0, y1), pack_bf(rs, rs));
        *reinterpret_cast<uint32_t*>(P.out + (size_t)win.y * DM + b * 8 + t3 * 2) =
            hadd2(fx.x, hmul2(__byte_perm(gv.x, gv.y, 0x7632), hadd2(fh.x, upd)));
        if (b == 0 && t3 == 0) st_relaxed(&g_epoch, epoch + 1);
      }
      PROF(31, t3 == 0, 36);
    }
    cluster_wait();
  } else {
    const int wg = warp >> 2;

    uint32_t tag;
    {
      uint32_t* const pmod = g_modp + rank * 2 * DM + (b >> 1) * 32 + lane;
      uint32_t* const pln = g_ln1 + (rb * 128 + cj * 16 + warp) * 4;
      const uint32_t cv = ldg_nc1(P.c + rank * 512 + tid * 2);
      const uint32_t epoch = ld_relaxed(&g_epoch);
      if (warp == 0) st_relaxed(pmod, 0);
      if (lane == 0) { st_b128(pln, 0, 0, 0, 0); st_b128(pln + 32, 0, 0, 0, 0); }
      asm volatile("setmaxnreg.inc.sync.aligned.u32 232;");
      sts1(par + tid * 4, pack_bf(silu_f(bf_lo(cv)), silu_f(bf_hi(cv))));
      bar_sync(1, 320);
      tag = epoch % 3 + 1;
#pragma unroll
      for (int part = 0; part < 3; part++) {
        if (part != 1) {
          const uint32_t xa = base + (2 + part / 2) * GST_BYTES + warp * 2048 + lane * 16;
          mbar_wait(bar_hx + part * 4, 0);
          float s0 = 0.f, s1 = 0.f, q0 = 0.f, q1 = 0.f;
#pragma unroll
          for (int q = 0; q < 4; q++) {
            const uint4 xv = lds4(xa + q * 512);
            const uint32_t u[4] = {xv.x, xv.y, xv.z, xv.w};
#pragma unroll
            for (int e = 0; e < 4; e++) { const float lo = bf_lo(u[e]), hi = bf_hi(u[e]); s0 += lo; s1 += hi; q0 += lo * lo; q1 += hi * hi; }
          }
          s0 += s1; q0 += q1;
#pragma unroll
          for (int o = 16; o > 0; o >>= 1) { s0 += __shfl_xor_sync(0xffffffffu, s0, o); q0 += __shfl_xor_sync(0xffffffffu, q0, o); }
          const float mean = s0 * (1.f / DM);
          float mb, sd;
          ln_scalars(mean, fmaxf(q0 * (1.f / DM) - mean * mean, 0.f), mb, sd);
          uint32_t ih, il;
          split_inv(sd, ih, il);
          if (lane == 0) st_b128(pln + part * 16, pack_bf(mb, mb), ih, il, tag);
          PROF(1, tid == 0 && part == 2, 4);
        } else {
          float acc[8];
#pragma unroll
          for (int e = 0; e < 8; e++) acc[e] = 0.f;
          const uint32_t wa = stage + (tid >> 2) * 64 + (((tid ^ (tid >> 3)) & 3) << 4), sa = par + (tid >> 3) * 4, sh = (tid & 4) ? 0x3244 : 0x1044;
          mbar_wait(bar_hw, 0);
#pragma unroll
          for (int p = 0; p < 8; p++) {
            const uint4 w = lds4(wa + p * 4096);
            const float s = __uint_as_float(__byte_perm(lds1(sa + p * 128), 0, sh));
            acc[0] += s * bf_lo(w.x); acc[1] += s * bf_hi(w.x); acc[2] += s * bf_lo(w.y); acc[3] += s * bf_hi(w.y);
            acc[4] += s * bf_lo(w.z); acc[5] += s * bf_hi(w.z); acc[6] += s * bf_lo(w.w); acc[7] += s * bf_hi(w.w);
          }
#pragma unroll
          for (int e = 0; e < 4; e++) {
            const bool up = lane & 16;
            acc[e] = (up ? acc[e + 4] : acc[e]) + __shfl_xor_sync(0xffffffffu, up ? acc[e] : acc[e + 4], 16);
          }
#pragma unroll
          for (int e = 0; e < 2; e++) {
            const bool up = lane & 8;
            acc[e] = (up ? acc[e + 2] : acc[e]) + __shfl_xor_sync(0xffffffffu, up ? acc[e] : acc[e + 2], 8);
          }
          {
            const bool up = lane & 4;
            acc[0] = (up ? acc[1] : acc[0]) + __shfl_xor_sync(0xffffffffu, up ? acc[0] : acc[1], 4);
          }
          sts1(base + 2 * GST_BYTES + warp * 2048 + ((lane & 3) * 8 + (lane >> 2)) * 4, __float_as_uint(acc[0]));
          bar_sync(1, 256);
          if (warp == 0) {
            float s = 0.f;
#pragma unroll
            for (int w8 = 0; w8 < 8; w8++) s += __uint_as_float(lds1(base + 2 * GST_BYTES + w8 * 2048 + lane * 4));
            st_relaxed(pmod, (__float_as_uint(s) & ~3u) | tag);
          }
          PROF(1, tid == 0, 3);
        }
      }
      cluster_wait();
      if (wg == 1) bar_arrive(2, 256);
    }

    float f0 = 0.f, f1 = 0.f;
    const uint32_t rempty = lane < 2 ? mapa(bempty, lane & 1) : 0;
    constexpr uint32_t GE = NSLOT * 8 + 32;
    float o[64], s[64];
#pragma unroll 1
    for (int ps = 0; ps < 3; ps++) {
      {
        const uint32_t xt = ps == 1 ? XT1 : XT2, wt = ps == 1 ? WT1 : WT2;
        const int nst = ps == 2 ? 28 : 14;
        if (ps == 0) {
          float ga[64], gb[64];
#pragma unroll
          for (int i = 0; i < 64; i++) { ga[i] = 0.f; gb[i] = 0.f; }
          uint32_t a[2][16];
          const uint32_t l = fresh_lane();
          uint32_t fa[4];
#pragma unroll
          for (int kk = 0; kk < 4; kk++) fa[kk] = (base + wg * 8192 + frag_offset(warp)) ^ (kk * 32);
          const uint32_t mt = par + (l & 3) * 16;
          auto fetch = [&](int i, uint32_t (&f)[16], uint32_t z) {
            mbar_wait(xfull + (i & 3) * 8, i >> 2);
#pragma unroll
            for (int kk = 0; kk < 4; kk++) ldmatrix4(fa[kk] + (i & 3) * GST_BYTES + z, f[4 * kk], f[4 * kk + 1], f[4 * kk + 2], f[4 * kk + 3]);
          };
          uint4 r0, r1;
          {
            const uint32_t t7 = (warp & 3) * 32 + l;
            const uint32_t* pm = g_modp + wg * DM + ((cj * 128 + t7 * 4) & (DM - 1));
            const uint32_t* pr = g_ln1 + (rb * 128 + warp * 16 + (l >> 2)) * 4;
            uint4 m0 = ld_relaxed4(pm), m1 = ld_relaxed4(pm + 2 * DM);
            r0 = ld_b128(pr); r1 = ld_b128(pr + 32);
            fetch(0, a[0], 0); fetch(1, a[1], 0);
            uint32_t n = 0;
            bool written = false;
#pragma unroll 1
            while (true) {
              uint32_t miss;
              asm volatile("{ .reg .pred p0, p1, p2, p3; .reg .b32 t, u;\n"
                           "lop3.b32 t, %1, %2, %19, 0x7e; lop3.b32 u, %3, %4, %19, 0x7e; or.b32 t, t, u; and.b32 t, t, 3; setp.ne.u32 p0, t, 0;\n"
                           "lop3.b32 t, %5, %6, %19, 0x7e; lop3.b32 u, %7, %8, %19, 0x7e; or.b32 t, t, u; and.b32 t, t, 3; setp.ne.u32 p1, t, 0;\n"
                           "setp.ne.u32 p2, %12, %19; setp.ne.u32 p3, %16, %19;\n"
                           "@p0 ld.relaxed.gpu.global.v4.u32 {%1, %2, %3, %4}, [%17];\n"
                           "@p1 ld.relaxed.gpu.global.v4.u32 {%5, %6, %7, %8}, [%17 + 8192];\n"
                           "@p2 ld.relaxed.gpu.global.v4.u32 {%9, %10, %11, %12}, [%18];\n"
                           "@p3 ld.relaxed.gpu.global.v4.u32 {%13, %14, %15, %16}, [%18 + 128];\n"
                           "or.pred p0, p0, p1; or.pred p2, p2, p3; vote.sync.any.pred p0, p0, 0xffffffff; vote.sync.any.pred p2, p2, 0xffffffff;\n"
                           "selp.u32 t, 1, 0, p0; selp.u32 u, 2, 0, p2; or.b32 %0, t, u; }"
                           : "=r"(miss), "+r"(m0.x), "+r"(m0.y), "+r"(m0.z), "+r"(m0.w), "+r"(m1.x), "+r"(m1.y), "+r"(m1.z), "+r"(m1.w),
                             "+r"(r0.x), "+r"(r0.y), "+r"(r0.z), "+r"(r0.w), "+r"(r1.x), "+r"(r1.y), "+r"(r1.z), "+r"(r1.w)
                           : "l"(pm), "l"(pr), "r"(tag) : "memory");
              if (!(miss & 1) && !written) {
                written = true;
                float c0 = untag_sum(m0.x, m1.x), c1 = untag_sum(m0.y, m1.y), c2 = untag_sum(m0.z, m1.z), c3 = untag_sum(m0.w, m1.w);
                if (wg) { c0 = 1.f + rbf(c0); c1 = 1.f + rbf(c1); c2 = 1.f + rbf(c2); c3 = 1.f + rbf(c3); }
                const uint32_t d = par + (t7 >> 2) * 64 + (t7 & 1) * 32 + (t7 & 2) * 2 + (wg ? 0 : 8);
                sts1(d, pack_bf(c0, c1));
                sts1(d + 16, pack_bf(c2, c3));
                mbar_arrive(bar_mod);
              }
              if (!miss) break;
              watchdog(n);
            }
          }
          const uint32_t zero = r0.w ^ tag;
          auto normalize = [&](uint32_t (&f)[16]) {
#pragma unroll
            for (int k = 0; k < 16; k += 2) { f[k] = ln_norm(f[k], r0.x, r0.y, r0.z); f[k + 1] = ln_norm(f[k + 1], r1.x, r1.y, r1.z); }
          };
          auto modulate = [&](int i, uint32_t (&f)[16]) {
#pragma unroll
            for (int kk = 0; kk < 4; kk++) {
              const uint4 m = lds4(mt + i * 256 + kk * 64);
              f[4 * kk] = MODUL(f[4 * kk], m.x, m.z); f[4 * kk + 1] = MODUL(f[4 * kk + 1], m.x, m.z);
              f[4 * kk + 2] = MODUL(f[4 * kk + 2], m.y, m.w); f[4 * kk + 3] = MODUL(f[4 * kk + 3], m.y, m.w);
            }
            keep(f);
            mbar_arrive_pred(xempty + (i & 3) * 8, l == 0);
          };
          auto publish = [&](int u, uint32_t (&f)[16]) {
#pragma unroll
            for (int kk = 0; kk < 4; kk++) stmatrix4(fa[kk] + OFF_STAGE + u * UNIT, f[4 * kk], f[4 * kk + 1], f[4 * kk + 2], f[4 * kk + 3]);
            __syncwarp();
            mbar_arrive_pred(bar_hpub + u * 8, l == 0);
          };
          auto multiply = [&](int i, uint32_t (&f)[16]) {
            mbar_wait(gfull + (i & 3) * 8, i >> 2);
            const uint64_t db = make_desc(base + (i & 3) * GST_BYTES + UNIT, 8192, 1024);
            wg_fence();
#pragma unroll
            for (int kk = 0; kk < 4; kk++) mma256_rs(ga, gb, f[4 * kk], f[4 * kk + 1], f[4 * kk + 2], f[4 * kk + 3], db + kk * 128);
            wg_commit();
          };
          auto next = [&](int i, uint32_t (&f)[16]) {
            wg_wait<1>();
            mbar_arrive_cl(rempty, GE + ((i + 2) & 3) * 8);
            uint32_t z = zero;
#pragma unroll
            for (int k = 0; k < 16; k += 2) asm volatile("lop3.b32 %0, %1, %2, %0, 0xA8;" : "+r"(z) : "r"(f[k]), "r"(f[k + 1]));
            fetch(i, f, z);
            normalize(f); modulate(i, f); multiply(i, f);
          };
          normalize(a[0]); normalize(a[1]);
          keep(a[0]); keep(a[1]);
          mbar_wait(bar_mod, 0);
          PROF(1, tid == 0, 2);
          modulate(0, a[0]); multiply(0, a[0]); publish(0, a[0]);
          modulate(1, a[1]); multiply(1, a[1]); publish(1, a[1]);
#pragma unroll 1
          for (int i = 2; i < NRS; i += 2) { next(i, a[0]); next(i + 1, a[1]); }
          wg_wait<1>();
          mbar_arrive_cl(rempty, GE + ((NRS + 2) & 3) * 8);
#pragma unroll 1
          for (int i = NRS; i < 14; i++) {
            mbar_wait(xfull + (i & 3) * 8, (i >> 2) & 1);
            mbar_wait(gfull + (i & 3) * 8, (i >> 2) & 1);
            const uint32_t xa = base + (i & 3) * GST_BYTES;
            const uint64_t da = make_desc(xa + wg * 8192, 16, 1024), db = make_desc(xa + UNIT, 8192, 1024);
            if (i == 13) bar_sync(2 + wg, 256);
            wg_fence();
#pragma unroll
            for (int kk = 0; kk < 4; kk++) mma256_ss(ga, gb, da + kk * 2, db + kk * 128, 1);
            wg_commit();
            if (i == 13) bar_arrive(3 - wg, 256);
            wg_wait<1>();
            uint32_t z = zero;
#pragma unroll
            for (int k = 0; k < 16; k += 2) asm volatile("lop3.b32 %0, %1, %2, %0, 0xA8;" : "+r"(z) : "r"(a[1][k]), "r"(a[1][k + 1]));
            mbar_arrive_cl(rempty, GE + ((i + 3) & 3) * 8 + z);
            mbar_arrive_pred(xempty + ((i + 3) & 3) * 8, l == 0 && i != NRS);
          }
          mbar_wait(xfull + 16, 1);
          wg_wait<0>();
          keep(ga); keep(gb);
#pragma unroll
          for (int i = 0; i < 64; i++) {
            asm volatile("mov.b32 %0, %1;" : "=f"(s[i]) : "f"(ga[i]));
            asm volatile("mov.b32 %0, %1;" : "=f"(o[i]) : "f"(gb[i]));
          }
        } else {
          float ga[64], gb[64];
#pragma unroll
          for (int i = 0; i < 64; i++) {
            asm volatile("mov.b32 %0, %1;" : "=f"(ga[i]) : "f"(s[i]));
            asm volatile("mov.b32 %0, %1;" : "=f"(gb[i]) : "f"(o[i]));
          }
#pragma unroll 1
          for (int i = 0; i < nst; i++) {
            mbar_wait(gfull + (i & 3) * 8, (i >> 2) & 1);
            const uint64_t da = make_desc(base + unit_of(xt, i & 3) + wg * 8192, 16, 1024), db = make_desc(base + unit_of(wt, i & 3), 8192, 1024);
            if (i == nst - 1) bar_sync(2 + wg, 256);
            wg_fence();
#pragma unroll
            for (int kk = 0; kk < 4; kk++) mma256_ss(ga, gb, da + kk * 2, db + kk * 128, kk ? 1 : i);
            wg_commit();
            if (i == nst - 1) bar_arrive(3 - wg, 256);
            wg_wait<1>();
            mbar_arrive_cl(rempty, GE + ((i + 3) & 3) * 8, i != 0);
            PROF(4, tid == 0 && (i & 3) == 0, 40 + (ps - 1) * 4 + i / 4);
          }
          wg_wait<0>();
          keep(ga); keep(gb);
#pragma unroll
          for (int i = 0; i < 64; i++) {
            asm volatile("mov.b32 %0, %1;" : "=f"(s[i]) : "f"(ga[i]));
            asm volatile("mov.b32 %0, %1;" : "=f"(o[i]) : "f"(gb[i]));
          }
        }
        mbar_arrive_cl(rempty, GE + (ps == 2 ? 24 : 8));
        if (ps == 2) break;
      }
      const uint32_t qw = base + wg * 8192, qt = QT >> (16 * ps), at = ps ? AT1 : AT0;
      {
        const uint32_t wt = ps ? WT1 : WT0;
        const uint64_t da0 = make_desc(qw + unit_of(qt, 2), 16, 1024), da1 = make_desc(qw + unit_of(qt, 3), 16, 1024);
        const uint64_t db0 = make_desc(base + unit_of(wt, 2), 8192, 1024), db1 = make_desc(base + unit_of(wt, 3), 8192, 1024);
        mbar_wait(gfull + 16, 1);
        bar_sync(2 + wg, 256);
        wg_fence();
#pragma unroll
        for (int kk = 0; kk < 4; kk++) mma_ss<1>(s, da0 + kk * 2, db0 + kk * 128, 1);
        wg_commit();
        mbar_wait(xfull + 24, 1);
        mbar_wait(gfull + 24, 1);
        wg_fence();
#pragma unroll
        for (int kk = 0; kk < 4; kk++) mma_ss<1>(s, da1 + kk * 2, db1 + kk * 128, 1);
        wg_commit();
        bar_arrive(3 - wg, 256);
        mbar_wait(ps == 0 ? bar_pread : bar_ofree + 8, 0);
        mbar_wait(bfull, 0);
        wg_wait<0>();
        keep(s);
        PROF(2, tid == 0, 8 + ps * 8);
        store_chunk<0>(s, qw + unit_of(qt, 0) + frag_offset(warp));
        store_chunk<1>(s, qw + unit_of(qt, 1) + frag_offset(warp));
        fence_async_smem();
        bar_sync(2 + wg, 256);
        wg_fence();
        issue_qk(s, qw + unit_of(qt, 0), qw + unit_of(qt, 1), base + unit_of(at, 0));
        wg_commit();
#pragma unroll
        for (int kk = 0; kk < 8; kk++) mma_ss<1>(o, (kk < 4 ? da0 : da1) + (kk & 3) * 2, (kk < 4 ? db0 : db1) + UNIT / 16 + (kk & 3) * 128, 1);
        wg_commit();
        bar_arrive(3 - wg, 256);
        wg_wait<1>();
        keep(s);
        mbar_arrive_cl(rempty, 0);
      }
      PROF(4, tid == 0 && ps == 1, 61);
      float l0 = 0.25f, l1 = 0.25f;
      auto step = [&](auto odd_c, const int j, uint32_t (&pw)[32], uint32_t (&pr)[32]) {
        constexpr bool ODD = decltype(odd_c)::value;
        const bool first = !ODD && (j & 2) == 0, last = ODD && j == 7;
        const uint32_t ph = (j >> 1) & 1;
        float i0, i1, a0, a1;
        if (first) { i0 = inv_quad_sum(l0); i1 = inv_quad_sum(l1); l0 = 0.f; l1 = 0.f; }
        bool redo = !ODD && (j | ps) == 0, again = false;
        while (true) {
          if (redo) {
            float m0 = fmaxf(s[0], s[1]), m1 = fmaxf(s[2], s[3]);
#pragma unroll
            for (int i = 1; i < 16; i++) { m0 = fmaxf(m0, fmaxf(s[4 * i], s[4 * i + 1])); m1 = fmaxf(m1, fmaxf(s[4 * i + 2], s[4 * i + 3])); }
            m0 = fmaxf(m0, __shfl_xor_sync(0xffffffffu, m0, 1)); m1 = fmaxf(m1, __shfl_xor_sync(0xffffffffu, m1, 1));
            m0 = fmaxf(m0, __shfl_xor_sync(0xffffffffu, m0, 2)); m1 = fmaxf(m1, __shfl_xor_sync(0xffffffffu, m1, 2));
            m0 *= SCL2; m1 *= SCL2;
            if (!first) {
              m0 = fmaxf(m0, f0); m1 = fmaxf(m1, f1);
              const float c0 = ex2(f0 - m0), c1 = ex2(f1 - m1);
              l0 *= c0; l1 *= c1;
              wg_wait<0>();
              keep(o);
#pragma unroll
              for (int i = 0; i < 16; i++) { o[4 * i] *= c0; o[4 * i + 1] *= c0; o[4 * i + 2] *= c1; o[4 * i + 3] *= c1; }
            }
            f0 = m0; f1 = m1;
          }
          float b0 = 0.f, b1 = 0.f;
          a0 = 0.f; a1 = 0.f;
#pragma unroll
          for (int i = 0; i < 16; i++) {
            const float e0 = ex2(fmaf(s[4 * i], SCL2, -f0)), e1 = ex2(fmaf(s[4 * i + 1], SCL2, -f0));
            const float e2 = ex2(fmaf(s[4 * i + 2], SCL2, -f1)), e3 = ex2(fmaf(s[4 * i + 3], SCL2, -f1));
            a0 += e0; b0 += e1; a1 += e2; b1 += e3;
            pw[2 * i] = pack_bf(e0, e1); pw[2 * i + 1] = pack_bf(e2, e3);
            if (i == VREL) {
#pragma unroll
              for (int k = 0; k < 2 * VREL + 2; k++) asm volatile("" : "+r"(pw[k])::"memory");
              mbar_wait(bar_mod, 0);
              wg_wait<0>();
              mbar_arrive_cl(rempty, ODD ? 16 : (j ? 0 : GE + 16), !again);
              if (!ODD) mbar_arrive_cl(rempty, GE + 24, !again && j == 0);
#pragma unroll
              for (int k = 4 * VREL + 4; k < 64; k++) asm volatile("" : "+f"(s[k])::"memory");
            }
          }
          a0 += b0; a1 += b1;
          if (redo) break;
          redo = __any_sync(0xffffffffu, !(a0 + a1 < 0x1p70f));
          if (first) {
            uint32_t m0 = __ballot_sync(0xffffffffu, a0 > 0x1p-50f), m1 = __ballot_sync(0xffffffffu, a1 > 0x1p-50f);
            m0 |= m0 >> 1; m1 |= m1 >> 1; m0 |= m0 >> 2; m1 |= m1 >> 2;
            redo = redo || (m0 & m1 & 0x11111111u) != 0x11111111u;
          }
          if (!redo) break;
          again = true;
        }
        l0 += a0; l1 += a1;
        keep(pw);
        keep(o);
        const uint32_t qo = qt >> (j ? 0 : 8);
        if (first) store_chunk<0>(o, i0, i1, qw + unit_of(qo, 0) + frag_offset(warp));
        keep(o);
        mbar_wait(bfull + (ODD ? 24 : 8), ph);
        bar_sync(2 + wg, 256);
        if (!last) {
          const uint32_t qn = qt >> (j >= 3 ? 8 : 0);
          wg_fence();
          issue_qk(s, qw + unit_of(qn, 0), qw + unit_of(qn, 1), base + unit_of(at, ODD ? 3 : 1));
          wg_commit();
          mbar_wait(bfull + (ODD ? 0 : 16), ODD ? ph ^ 1 : ph);
        }
        if (first) { store_chunk<1>(o, i0, i1, qw + unit_of(qo, 1) + frag_offset(warp)); keep(o); }
        wg_fence();
        issue_pv(o, pw, base + unit_of(at, ODD ? (last ? 3 : 0) : 2), !first);
        wg_commit();
        bar_arrive(3 - wg, 256);
        wg_wait<1>();
        keep(s);
        mbar_arrive_cl(rempty, ODD ? 24 : 8, !last);
        if (first) { fence_async_smem(); mbar_arrive_pred(bar_ofull + wg * 8, j); }
        PROF(4, tid == 0 && ps == 1, 51 + j);
      };
      uint32_t pa[32], pb[32];
#pragma unroll 1
      for (int j = 0; j < 8; j += 2) {
        step(std::false_type{}, j, pa, pb);
        step(std::true_type{}, j + 1, pb, pa);
      }
      {
        const float i0 = inv_quad_sum(l0), i1 = inv_quad_sum(l1);
        wg_wait<0>();
        keep(o);
        mbar_arrive_cl(rempty, 24);
        store_chunk<0>(o, i0, i1, qw + unit_of(qt, 2) + frag_offset(warp));
        store_chunk<1>(o, i0, i1, qw + unit_of(qt, 3) + frag_offset(warp));
        fence_async_smem();
        mbar_arrive(bar_ofull + 16 + wg * 8);
      }
      PROF(2, tid == 0, 10 + ps * 8);
    }

    const int ln = fresh_lane(), g = ln >> 2, tq = ln & 3, ct = warp * 32 + ln;
    const bool lane0 = ln == 0;
    const int lrow0 = warp * 16 + g;
    const int grow0 = rb * 128 + lrow0;
    const uint32_t res = base + OFF_RES, trow = res + wg * 8192 + frag_offset(warp);
    uint32_t xr[32];
    uint4 sv[4], own;
    uint32_t* sp[4];
#pragma unroll
    for (int k = 0; k < 4; k++) sp[k] = g_stats + ((((tq >> 1) * 4 + k) ^ cj) * SEQ + grow0 + (tq & 1) * 8) * 4;
    {
      const uint64_t da = make_desc(base + wg * 8192, 16, 1024), db = make_desc(base, 8192, 1024);
      constexpr int U = UNIT / 16;
#define HALF_STAGE(acc, xu, wu) _Pragma("unroll") for (int kk = 0; kk < 4; kk++) mma_ss<1>(acc, da + (xu) * U + kk * 2, db + (wu) * U + kk * 128, 1)
      PROF(10, ct == PT, 19); STAMP(0);
      cluster_arrive();
      mbar_wait(gfull, 1);
      mbar_wait(gfull + 8, 1);
      bar_sync(2 + wg, 256);
      wg_fence();
      HALF_STAGE(o, 7, 1);
      HALF_STAGE(o, 8, 3);
      wg_commit();
      STAMP(16);
      mbar_wait(gfull + 16, 1);
      STAMP(17);
      wg_fence();
      HALF_STAGE(o, 6, 11);
      wg_commit();
      bar_arrive(3 - wg, 256);
      mbar_wait(bar_par, 0);
      uint32_t* xo = g_xch + ((size_t)b * 8 * 256 + ct) * 4;
      const uint32_t* xi = g_xch + ((size_t)(b ^ 2) * 8 * 256 + ct) * 4;
      const uint32_t par1 = (~lds1(par + PAR_CONST + 4) & 1) << 16;
      uint32_t ga[16];
      uint4 bw[8];
#define LOAD_PAR _Pragma("unroll") for (int i = 0; i < 8; i++) {                                                               \
        ga[2 * i] = lds1(par + PAR_T2 + i * 128 + tq * 16 + 12); ga[2 * i + 1] = lds1(par + PAR_T2 + i * 128 + 64 + tq * 16 + 12); \
        bw[i] = lds4(par + PAR_T1 + i * 64 + tq * 16);                                                                          \
        if (!(g & 1)) { bw[i].x = 0x3f803f80u; bw[i].y = 0x3f803f80u; }                                                         \
      }
      if (PPOS == 0) LOAD_PAR
      wg_wait<1>();
      mbar_arrive_pred(bar_rel, lane0);
      wg_wait<0>();
      keep(o);
      mbar_arrive_pred(bar_ring, lane0);
      PROF(8, ct == PT, 20); STAMP(1);
#define SEND(i) st_b128(xo + (i) * 1024, (pack_bf(o[8 * (i)], o[8 * (i) + 1]) & ~0x10000u) | par1, pack_bf(o[8 * (i) + 2], o[8 * (i) + 3]), \
                        pack_bf(o[8 * (i) + 4], o[8 * (i) + 5]), pack_bf(o[8 * (i) + 6], o[8 * (i) + 7]))
#pragma unroll
      for (int i = 0; i < NS1; i++) SEND(i);
      PROF(8, ct == PT, 21); STAMP(2);
      bar_sync(2 + wg, 256);
      wg_fence();
      HALF_STAGE(s, 7, 0);
      HALF_STAGE(s, 8, 2);
      HALF_STAGE(s, 6, 10);
      wg_commit();
      bar_arrive(3 - wg, 256);
      STAMP(18);
      mbar_wait(gfull + 24, 1);
#pragma unroll
      for (int i = NS1; i < 8; i++) SEND(i);
      uint4 v[8];
#pragma unroll
      for (int i = 0; i < 4; i++) v[i] = ld_b128(xi + i * 1024);
      if (PPOS == 1) LOAD_PAR
      STAMP(19);
      mbar_wait(bar_xres, 0);
      wg_wait<0>();
      mbar_arrive_pred(bar_ring + 8, lane0);
      bar_sync(2 + wg, 256);
      STAMP(20);
#pragma unroll
      for (int i = 4; i < 8; i++) v[i] = ld_b128(xi + i * 1024);
      mbar_wait(bar_xres, 0);
      wg_fence();
      HALF_STAGE(s, 9, 4);
      wg_commit();
      mbar_wait(bar_rx, 0);
      wg_fence();
      HALF_STAGE(s, 1, 5);
      wg_commit();
      bar_arrive(3 - wg, 256);
      STAMP(21);
      wg_wait<0>();
      keep(s);
      mbar_arrive_pred(bar_ring + 16, lane0);
      PROF(10, ct == PT, 23); STAMP(4);
#pragma unroll
      for (int i = 0; i < 16; i += 2) ldmatrix4((trow ^ ((i & 7) << 4)) + (i >> 3) * 16384, xr[2 * i], xr[2 * i + 1], xr[2 * i + 2], xr[2 * i + 3]);
      if (PPOS == 2) LOAD_PAR
      uint32_t pk[32];
      pack_p(s, pk);
      keep(pk);
      {
        uint32_t n = 0, miss;
        do {
          miss = 0;
#pragma unroll
          for (int i = 0; i < 8; i++) miss |= v[i].x ^ par1;
          miss = __any_sync(0xffffffffu, miss & 0x10000u);
          if (miss) {
#pragma unroll
            for (int i = 0; i < 8; i++)
              asm volatile("{ .reg .pred p; .reg .b32 t; xor.b32 t, %0, %5; and.b32 t, t, 0x10000; setp.ne.u32 p, t, 0;\n"
                           "@p ld.relaxed.gpu.global.v4.u32 {%0, %1, %2, %3}, [%4]; }"
                           : "+r"(v[i].x), "+r"(v[i].y), "+r"(v[i].z), "+r"(v[i].w) : "l"(xi + i * 1024), "r"(par1) : "memory");
          }
          watchdog(n);
        } while (miss);
      }
      PROF(8, ct == PT, 22); STAMP(3);
#pragma unroll
      for (int k = 0; k < 4; k++) sv[k] = ESV ? ld_b128(sp[k]) : make_uint4(0, 0, 0, 0);
      float ds[4] = {0.f, 0.f, 0.f, 0.f}, dl[4] = {0.f, 0.f, 0.f, 0.f}, q0[4] = {0.f, 0.f, 0.f, 0.f}, q1[4] = {0.f, 0.f, 0.f, 0.f};
#pragma unroll
      for (int i = 0; i < 8; i++) {
        const uint32_t u0 = hfma2(ga[2 * i], hadd2(pk[4 * i], v[i].x & ~0x10000u), xr[4 * i]);
        const uint32_t u1 = hfma2(ga[2 * i], hadd2(pk[4 * i + 1], v[i].y), xr[4 * i + 1]);
        const uint32_t u2 = hfma2(ga[2 * i + 1], hadd2(pk[4 * i + 2], v[i].z), xr[4 * i + 2]);
        const uint32_t u3 = hfma2(ga[2 * i + 1], hadd2(pk[4 * i + 3], v[i].w), xr[4 * i + 3]);
        xr[4 * i] = u0; xr[4 * i + 1] = u1; xr[4 * i + 2] = u2; xr[4 * i + 3] = u3;
        mma16816(ds, u0, u1, u2, u3, bw[i].x, bw[i].y);
        mma16816(dl, u0, u1, u2, u3, bw[i].z, bw[i].w);
        mma16816(q0, u0, u1, u2, u3, u0, u2);
        mma16816(q1, u0, u1, u2, u3, u1, u3);
      }
      const float sqa = __shfl_sync(0xffffffffu, (g & 1) ? q0[1] : q0[0], g * 4 + (g >> 1));
      const float sqb = __shfl_sync(0xffffffffu, (g & 1) ? q1[3] : q1[2], g * 4 + (g >> 1));
      own = (tq & 1) ? make_uint4(__float_as_uint(ds[2]), __float_as_uint(sqb), __float_as_uint(ds[3] + dl[3]), tag)
                                 : make_uint4(__float_as_uint(ds[0]), __float_as_uint(sqa), __float_as_uint(ds[1] + dl[1]), tag);
      if (tq < 2) st_b128(sp[0], own.x, own.y, own.z, own.w);
    }
    PROF(8, ct == PT, 29); STAMP(5);
    uint32_t mm, ih, il;
    float rbest;
    uint32_t wf[128];
    const uint32_t frow = (ln & 7) + (ln >> 4) * 8;
    const uint32_t wfo = base + (warp & 1) * 8192 + frow * 64 + ((((ln >> 3) & 1) ^ ((frow >> 1) & 3)) << 4);
#define LOAD_WF(m) _Pragma("unroll") for (int f = 0; f < 16; f++) {                                                   \
      const int r = ((f >> 1) * 4 + (m) * 2 + (f & 1)) * 4;                                                           \
      ldmatrix4t(((wfo + unit_of((m) ? FT_U : FT_G, warp >> 1)) ^ ((f & 1) * 32)) + (f >> 1) * 1024, wf[r], wf[r + 1], wf[r + 2], wf[r + 3]); \
    }
    bool early, wait1;
    {
#pragma unroll
      for (int i = 0; i < 16; i += 2) stmatrix4((trow ^ ((i & 7) << 4)) + (i >> 3) * 16384, xr[2 * i], xr[2 * i + 1], xr[2 * i + 2], xr[2 * i + 3]);
      const uint4 cst = lds4(par + PAR_CONST);
      const float A1 = __uint_as_float(cst.x), A2 = __uint_as_float(cst.z);
      uint32_t n = 0;
      early = false; wait1 = false;
#pragma unroll 1
      while (true) {
        uint32_t miss;
        asm volatile("{ .reg .pred p0, p1, p2, p3; .reg .b64 u, v; .reg .b128 w;\n"
                     "setp.ge.u32 p0, %22, 2; setp.ne.and.u32 p0, %4, %21, p0; setp.ne.u32 p1, %8, %21; setp.ne.u32 p2, %12, %21; setp.ne.u32 p3, %16, %21;\n"
                     "@p0 ld.relaxed.gpu.global.v4.u32 {%1, %2, %3, %4}, [%17];\n"
                     "@p1 ld.relaxed.gpu.global.v4.u32 {%5, %6, %7, %8}, [%18];\n"
                     "@p2 ld.relaxed.gpu.global.v4.u32 {%9, %10, %11, %12}, [%19];\n"
                     "@p3 ld.relaxed.gpu.global.v4.u32 {%13, %14, %15, %16}, [%20];\n"
                     "or.pred p0, p0, p1; or.pred p2, p2, p3; or.pred p0, p0, p2; vote.sync.any.pred p0, p0, 0xffffffff; selp.u32 %0, 1, 0, p0; }"
                     : "=r"(miss), "+r"(sv[0].x), "+r"(sv[0].y), "+r"(sv[0].z), "+r"(sv[0].w), "+r"(sv[1].x), "+r"(sv[1].y), "+r"(sv[1].z), "+r"(sv[1].w),
                       "+r"(sv[2].x), "+r"(sv[2].y), "+r"(sv[2].z), "+r"(sv[2].w), "+r"(sv[3].x), "+r"(sv[3].y), "+r"(sv[3].z), "+r"(sv[3].w)
                     : "l"(sp[0]), "l"(sp[1]), "l"(sp[2]), "l"(sp[3]), "r"(tag), "r"(tq) : "memory");
        if (!miss) break;
        wait1 = true;
        if (!early && (b >= NFFN || __all_sync(0xffffffffu, mbar_test(bar_box + (warp >> 1) * 8, 0)))) {
          early = true;
          LOAD_WF(0);
          __syncwarp();
          mbar_arrive_pred(bar_gate, lane0);
        }
        watchdog(n);
      }
      const uint4 v0 = tq < 2 ? own : sv[0], v1 = sv[1], v2 = sv[2], v3 = sv[3];
      PROF(8, ct == PT, 30); STAMP(6);
      float su = (__uint_as_float(v0.x) + __uint_as_float(v1.x)) + (__uint_as_float(v2.x) + __uint_as_float(v3.x));
      float sq = (__uint_as_float(v0.y) + __uint_as_float(v1.y)) + (__uint_as_float(v2.y) + __uint_as_float(v3.y));
      float dt = (__uint_as_float(v0.z) + __uint_as_float(v1.z)) + (__uint_as_float(v2.z) + __uint_as_float(v3.z));
      su += __shfl_xor_sync(0xffffffffu, su, 2); sq += __shfl_xor_sync(0xffffffffu, sq, 2); dt += __shfl_xor_sync(0xffffffffu, dt, 2);
      const float m = su * (1.f / DM);
      float mb, sd;
      ln_scalars(m, fmaxf(sq * (1.f / DM) - m * m, 0.f), mb, sd);
      const float inv = rcp(sd);
      rbest = (dt - mb * A1) * inv + A2;
      mm = pack_bf(mb, mb);
      ih = pack_bf(inv, inv);
      const float lo = inv - bf_lo(ih);
      il = pack_bf(lo, lo);
    }
    int ibest;
    {
      const uint32_t bits = __float_as_uint(rbest);
      const uint32_t key = (((int)bits < 0 ? ~bits : bits | 0x80000000u) & ~0x1ffu) | ((127 - lrow0 - (tq & 1) * 8) << 2) | tag;
      sts1(par + PAR_RED + warp * 4, __reduce_max_sync(0xffffffffu, key));
      PROF(8, ct == PT, 38); STAMP(7);
      uint32_t waited;
      asm volatile("{ .reg .pred p, q; setp.ne.u32 p, %1, 0; barrier.cta.red.or.pred q, 1, 256, p; selp.u32 %0, 1, 0, q; }" : "=r"(waited) : "r"((uint32_t)(wait1 && (wg || CW0))) : "memory");
      const uint4 ka = lds4(par + PAR_RED), kb = lds4(par + PAR_RED + 16);
      const uint32_t k2 = max(max(max(ka.x, ka.y), max(ka.z, ka.w)), max(max(kb.x, kb.y), max(kb.z, kb.w)));
      if (ct == 0 && ((cj & CWM) == 0 || (CWL && !waited))) st_relaxed(g_cand + rb, k2);
      ibest = 127 - ((k2 >> 2) & 127);
    }
    PROF(8, ct == PT, 39); STAMP(8);
    if ((ibest >> 4) == warp) {
      const int src = (ibest & 7) * 4 + ((ibest >> 3) & 1), ch = g * 2;
      const uint32_t cm = __shfl_sync(0xffffffffu, mm, src), ch_ = __shfl_sync(0xffffffffu, ih, src), cl = __shfl_sync(0xffffffffu, il, src);
      const uint32_t xa = res + (ch >> 3) * 16384 + ibest * 128 + (((ch & 7) ^ (ibest & 7)) << 4) + tq * 4;
      const uint32_t x0 = lds1(xa), x1 = lds1(xa ^ 16);
      const uint2 p0 = lds2(par + PAR_T2 + ch * 64 + tq * 16), p1 = lds2(par + PAR_T2 + ch * 64 + 64 + tq * 16);
      uint32_t* dst = g_row + rb * 2 * DM + cj * 128 + ln * 4;
      st_pairs(dst, ln_mod(x0, cm, ch_, cl, p0.x, p0.y), ln_mod(x1, cm, ch_, cl, p1.x, p1.y), tag);
      st_pairs(dst + DM, x0, x1, tag);
      __syncwarp();
    }
    PROF(8, ct == PT, 37); STAMP(9);
    uint32_t wd[64];
    const uint32_t wda = base + unit_of(FT_D, warp >> 1) + (warp & 1) * 8192 + frow * 128 + ((((ln >> 3) & 1) ^ (ln & 7)) << 4);
#define LOAD_WD(f) ldmatrix4t((wda ^ ((((f) >> 1) & 3) * 32)) + ((f) >> 3) * 4096 + ((f) & 1) * 2048, wd[4 * (f)], wd[4 * (f) + 1], wd[4 * (f) + 2], wd[4 * (f) + 3])
    if (!early) {
      if (b < NFFN) mbar_wait(bar_box + (warp >> 1) * 8, 0);
      LOAD_WF(0);
      __syncwarp();
      mbar_arrive_pred(bar_gate, lane0);
    }
    if (b < NFFN) {
      const uint32_t own = base + unit_of(FT_G, warp >> 1) + (warp & 1) * 8192;
      mbar_wait(bar_box + (4 + (warp >> 1)) * 8, 0);
      LOAD_WF(1);
      uint32_t* const ydst = g_ypart + ((size_t)(warp * 16 + tq * 2) * NFFN + b) * 8 + g;
      PROF(8, ct == PT, 31); STAMP(10);
      mbar_wait(bar_box + (8 + (warp >> 1)) * 8, 0);
#pragma unroll
      for (int f = 0; f < WDE; f++) LOAD_WD(f);
      STAMP(11);
      mbar_wait(bar_sel, 0);
      PROF(8, ct == PT, 33); STAMP(12);
      float d[8][4];
#pragma unroll
      for (int i = 0; i < 4; i++) { d[i][0] = 0.f; d[i][1] = 0.f; d[i][2] = 0.f; d[i][3] = 0.f; }
#pragma unroll
      for (int ks = 0; ks < 8; ks++) {
        const uint2 hb = lds2(own + 256 + ks * 32 + tq * 8);
#pragma unroll
        for (int mt = 0; mt < 4; mt++) {
          const int r = ks * 16 + mt * 4;
          mma16816(d[mt], wf[r], wf[r + 1], wf[r + 2], wf[r + 3], hb.x, hb.y);
        }
      }
      sts2(own + (tq * 8 + g) * 8, __float_as_uint((tq & 2) ? ((tq & 1) ? d[1][2] : d[1][0]) : ((tq & 1) ? d[0][2] : d[0][0])),
           __float_as_uint((tq & 2) ? ((tq & 1) ? d[3][2] : d[3][0]) : ((tq & 1) ? d[2][2] : d[2][0])));
      bar_sync(1, 256);
      uint32_t ab[4];
      {
        float G = 0.f, U = 0.f;
        uint2 pv[8];
#pragma unroll
        for (int w8 = 0; w8 < 8; w8++) pv[w8] = lds2(base + ln * 8 + ((FT_G >> (w8 >> 1) * 4) & 15) * UNIT + (w8 & 1) * 8192);
#pragma unroll
        for (int w8 = 0; w8 < 8; w8 += 2) {
          G += __uint_as_float(pv[w8].x) + __uint_as_float(pv[w8 + 1].x);
          U += __uint_as_float(pv[w8].y) + __uint_as_float(pv[w8 + 1].y);
        }
#pragma unroll
        for (int f = WDE; f < 16; f++) LOAD_WD(f);
        const float act = rbf(silu_f(rbf(G))) * rbf(U);
        const uint32_t pk = pack_bf(act, __shfl_down_sync(0xffffffffu, act, 1));
#pragma unroll
        for (int i = 0; i < 4; i++) ab[i] = __shfl_sync(0xffffffffu, pk, i * 8 + tq * 2);
      }
      PROF(8, ct == PT, 34); STAMP(13);
#pragma unroll
      for (int mt = 0; mt < 8; mt++) {
        d[mt][0] = 0.f; d[mt][1] = 0.f; d[mt][2] = 0.f; d[mt][3] = 0.f;
        mma16816(d[mt], wd[mt * 8], wd[mt * 8 + 1], wd[mt * 8 + 2], wd[mt * 8 + 3], ab[0], ab[1]);
        mma16816(d[mt], wd[mt * 8 + 4], wd[mt * 8 + 5], wd[mt * 8 + 6], wd[mt * 8 + 7], ab[2], ab[3]);
      }
#pragma unroll
      for (int i = 0; i < 4; i++) {
        const int m4 = (i >> 1) * 4, e = (i & 1) * 2;
        const float y = (tq & 2) ? ((tq & 1) ? d[m4 + 3][e] : d[m4 + 2][e]) : ((tq & 1) ? d[m4 + 1][e] : d[m4][e]);
        st_relaxed(ydst + (m4 * 2 + (i & 1)) * NFFN * 8, tagf(y, tag));
      }
      PROF(8, ct == PT, 35); STAMP(14);
    }
    mbar_wait(bar_sel, 0);
    mbar_arrive_pred(bar_win, ct == 0);
    const int iwin = lds1(par + PAR_CONST + 60) & 0x7ff;
    {
      const uint32_t mm0 = __shfl_sync(0xffffffffu, mm, ln & ~1), mm1 = __shfl_sync(0xffffffffu, mm, ln | 1);
      const uint32_t ih0 = __shfl_sync(0xffffffffu, ih, ln & ~1), ih1 = __shfl_sync(0xffffffffu, ih, ln | 1);
      const uint32_t il0 = __shfl_sync(0xffffffffu, il, ln & ~1), il1 = __shfl_sync(0xffffffffu, il, ln | 1);
      const bool mine = (iwin >> 4) == rb * 8 + warp;
#pragma unroll 1
      for (int hf = 0; hf < 2; hf++) {
        uint32_t x[16];
#pragma unroll
        for (int i = 0; i < 8; i += 2) ldmatrix4((trow ^ (i << 4)) + hf * 16384, x[2 * i], x[2 * i + 1], x[2 * i + 2], x[2 * i + 3]);
#pragma unroll
        for (int i = 0; i < 8; i++) {
          const uint4 pv = lds4(par + PAR_T2 + (hf * 8 + i) * 64 + tq * 16);
          x[2 * i] = hadd2(x[2 * i], hmul2(pv.z, ln_mod(x[2 * i], mm0, ih0, il0, pv.x, pv.y)));
          x[2 * i + 1] = hadd2(x[2 * i + 1], hmul2(pv.z, ln_mod(x[2 * i + 1], mm1, ih1, il1, pv.x, pv.y)));
        }
        if (mine) {
          uint32_t* dst = reinterpret_cast<uint32_t*>(P.out + (size_t)grow0 * DM + cj * 128 + hf * 64) + tq;
#pragma unroll
          for (int i = 0; i < 8; i++) {
            if (grow0 != iwin) dst[i * 4] = x[2 * i];
            if (grow0 + 8 != iwin) dst[i * 4 + 4 * DM] = x[2 * i + 1];
          }
        } else {
#pragma unroll
          for (int i = 0; i < 8; i += 2) stmatrix4((trow ^ (i << 4)) + hf * 16384, x[2 * i], x[2 * i + 1], x[2 * i + 2], x[2 * i + 3]);
          fence_async_smem();
          __syncwarp();
          if (elect_one()) {
            tma2d_store(&maps.out, res + hf * 16384 + warp * 2048, cj * 128 + hf * 64, rb * 128 + warp * 16);
            asm volatile("cp.async.bulk.commit_group;" ::: "memory");
          }
        }
      }
      asm volatile("cp.async.bulk.wait_group.read 0;" ::: "memory");
    }
    PROF(8, ct == PT, 11); STAMP(15);
    cluster_wait();
  }
}

typedef CUresult (*EncodeFn)(CUtensorMap*, CUtensorMapDataType, cuuint32_t, void*, const cuuint64_t*, const cuuint64_t*,
                             const cuuint32_t*, const cuuint32_t*, CUtensorMapInterleave, CUtensorMapSwizzle,
                             CUtensorMapL2promotion, CUtensorMapFloatOOBfill);

void map2d(EncodeFn enc, CUtensorMap* m, const void* p, uint64_t rows, uint64_t cols, uint32_t brows) {
  cuuint64_t dims[2] = {cols, rows}, strides[1] = {cols * 2};
  cuuint32_t box[2] = {64, brows}, es[2] = {1, 1};
  enc(m, CU_TENSOR_MAP_DATA_TYPE_BFLOAT16, 2, const_cast<void*>(p), dims, strides, box, es, CU_TENSOR_MAP_INTERLEAVE_NONE,
      CU_TENSOR_MAP_SWIZZLE_128B, CU_TENSOR_MAP_L2_PROMOTION_L2_256B, CU_TENSOR_MAP_FLOAT_OOB_FILL_NONE);
}
void map2d_narrow(EncodeFn enc, CUtensorMap* m, const void* p, uint64_t rows, uint64_t cols, uint32_t brows) {
  cuuint64_t dims[2] = {cols, rows}, strides[1] = {cols * 2};
  cuuint32_t box[2] = {32, brows}, es[2] = {1, 1};
  enc(m, CU_TENSOR_MAP_DATA_TYPE_BFLOAT16, 2, const_cast<void*>(p), dims, strides, box, es, CU_TENSOR_MAP_INTERLEAVE_NONE,
      CU_TENSOR_MAP_SWIZZLE_64B, CU_TENSOR_MAP_L2_PROMOTION_L2_64B, CU_TENSOR_MAP_FLOAT_OOB_FILL_NONE);
}
void map3d(EncodeFn enc, CUtensorMap* m, const void* p, uint64_t rows, uint64_t cols, uint32_t brows, uint32_t nch) {
  cuuint64_t dims[3] = {64, rows, cols / 64}, strides[2] = {cols * 2, 128};
  cuuint32_t box[3] = {64, brows, nch}, es[3] = {1, 1, 1};
  enc(m, CU_TENSOR_MAP_DATA_TYPE_BFLOAT16, 3, const_cast<void*>(p), dims, strides, box, es, CU_TENSOR_MAP_INTERLEAVE_NONE,
      CU_TENSOR_MAP_SWIZZLE_128B, CU_TENSOR_MAP_L2_PROMOTION_L2_256B, CU_TENSOR_MAP_FLOAT_OOB_FILL_NONE);
}

}

extern "C" void kernel_launch(void* const* d_in, const int* in_sizes, int n_in, void* d_out, int out_size) {
  (void)in_sizes; (void)n_in; (void)out_size;
  static EncodeFn enc = nullptr;
  if (!enc) {
    void* fn = nullptr;
    cudaDriverEntryPointQueryResult st;
    cudaGetDriverEntryPoint("cuTensorMapEncodeTiled", &fn, cudaEnableDefault, &st);
    enc = (EncodeFn)fn;
    cudaFuncSetAttribute(fused_kernel, cudaFuncAttributeMaxDynamicSharedMemorySize, SMEM_BYTES);
  }
  Maps maps;
  map2d(enc, &maps.x, d_in[0], SEQ, DM, 128);
  map2d(enc, &maps.out, d_out, SEQ, DM, 16);
  map3d(enc, &maps.wq, d_in[3], DM, NQ, 64, 2);
  map3d(enc, &maps.k, d_in[1], 4 * SK, 128, 128, 1);
  map3d(enc, &maps.v, d_in[2], 4 * SK, 128, 128, 1);
  map3d(enc, &maps.wo, d_in[4], NQ, DM, 64, 2);
  map2d_narrow(enc, &maps.wg, d_in[7], DM, FF, 256);
  map2d_narrow(enc, &maps.wu, d_in[8], DM, FF, 256);
  map3d(enc, &maps.wd, d_in[9], FF, DM, 32, 4);
  map2d_narrow(enc, &maps.wm, d_in[11], DM, NMOD, 256);
  Ptrs p;
  p.x = (const __nv_bfloat16*)d_in[0];
  p.w_r = (const __nv_bfloat16*)d_in[6];
  p.w_gate = (const __nv_bfloat16*)d_in[7];
  p.w_up = (const __nv_bfloat16*)d_in[8];
  p.w_down = (const __nv_bfloat16*)d_in[9];
  p.c = (const __nv_bfloat16*)d_in[10];
  p.w_mod = (const __nv_bfloat16*)d_in[11];
  p.out = (__nv_bfloat16*)d_out;
  fused_kernel<<<NMAIN + NHELP, 384, SMEM_BYTES>>>(maps, p);
}
```

```cpp
#include <cuda_runtime.h>
#include <cuda_bf16.h>
#include <cuda.h>
#include <stdint.h>
#include <type_traits>

#define HD 2
#define HDX 2
#define XF 4
#define XE 32
#define XR 0
#define NRS 8
#define FPACE 3
#define GOST 20
#define WB 3
#define WN 24
#define RES0 17
#define RES1 20
#define HU 32
#define NS1 6
#define PG0 0
#define PSL 0
#define CWM 7
#define WDE 16
#define CWL 1
#define CW0 0
#define ESV 1
#define PPOS 1
#define FB0 0
#define FB2 8
#define OPS 8192
#define OFL 0
#define ODS 8
#define MODUL hfma2
#define VREL 7
#define E0 3

namespace {

constexpr int SEQ = 2048, DM = 1024, NQ = 4096, SK = 2048, WIN = 512, FF = 3584, NMOD = 6144;
constexpr int NMAIN = 128, NHELP = 4, NFFN = 112;
constexpr int NSLOT = 4, SLOT_BYTES = 32768, UNIT = 16384, GST_BYTES = 3 * UNIT;
constexpr uint32_t XT1 = 0xDCBA, XT2 = 0x9687;
constexpr uint32_t WT0 = 0xA741, WT1 = 0x7420, WT2 = 0x4A20;
constexpr uint32_t AT0 = WT1, AT1 = WT2;
constexpr uint32_t QT = 0xDC9696DC;
constexpr int OFF_STAGE = 12 * UNIT;
constexpr uint32_t FT_G = 0x07B3, FT_U = 0xA628, FT_D = 0x5149;
constexpr int OFF_RES = 12 * UNIT;
constexpr int OFF_PAR = 14 * UNIT;
constexpr int OFF_BAR = OFF_PAR + 2528;
constexpr int SMEM_BYTES = OFF_BAR + 544;
static_assert(SMEM_BYTES <= 232448, "smem");

constexpr int PAR_T1 = 0;
constexpr int PAR_T2 = 512;
constexpr int PAR_CONST = 1536;
constexpr int PAR_RED = 1600;
constexpr int PAR_SINK = 2176;

struct Maps {
  CUtensorMap x, wq, k, v, wo, wg, wu, wd, wm, out;
};
struct Ptrs {
  const __nv_bfloat16 *x, *w_r, *c, *w_mod, *w_gate, *w_up, *w_down;
  __nv_bfloat16* out;
};

__device__ __align__(1024) uint8_t g_act[16 * 80 * UNIT];
__device__ __align__(128) uint32_t g_mod[NMOD];
__device__ __align__(128) uint32_t g_modp[2 * 2 * DM];
__device__ __align__(128) uint32_t g_ln1[SEQ * 4];
__device__ __align__(128) uint32_t g_cnt_h[16 * 32];
__device__ __align__(128) uint32_t g_cnt_o[128 * 32];
__device__ __align__(128) uint32_t g_xch[NMAIN * 8 * 256 * 4];
__device__ __align__(128) uint32_t g_stats[8 * SEQ * 4];
__device__ __align__(128) uint32_t g_cand[32];
__device__ __align__(128) uint32_t g_row[16 * 2 * DM];
__device__ __align__(128) uint32_t g_ypart[NMAIN * NFFN * 8];
__device__ uint32_t g_epoch;

__device__ __forceinline__ uint32_t fresh_lane() { uint32_t l; asm volatile("mov.u32 %0, %%laneid;" : "=r"(l)); return l; }
__device__ __forceinline__ uint32_t frag_offset(int warp) {
  const uint32_t l = fresh_lane();
  return ((warp & 3) * 16 + (l & 15)) * 128 + (((l >> 4) ^ (l & 7)) << 4);
}
__device__ __forceinline__ bool elect_one() {
  uint32_t p;
  asm volatile("{ .reg .pred q; elect.sync _|q, 0xffffffff; selp.u32 %0, 1, 0, q; }" : "=r"(p));
  return p;
}
__device__ __forceinline__ uint32_t smem_u32(const void* p) { return (uint32_t)__cvta_generic_to_shared(p); }
__device__ __forceinline__ void mbar_init(uint32_t bar, uint32_t cnt) {
  asm volatile("mbarrier.init.shared::cta.b64 [%0], %1;" ::"r"(bar), "r"(cnt) : "memory");
}
__device__ __forceinline__ void mbar_expect_tx(uint32_t bar, uint32_t bytes) {
  asm volatile("mbarrier.arrive.expect_tx.shared::cta.b64 _, [%0], %1;" ::"r"(bar), "r"(bytes) : "memory");
}
__device__ __forceinline__ void mbar_arrive(uint32_t bar) {
  asm volatile("mbarrier.arrive.shared::cta.b64 _, [%0];" ::"r"(bar) : "memory");
}
__device__ __forceinline__ void mbar_arrive_pred(uint32_t bar, bool p) {
  asm volatile("{ .reg .pred p; setp.ne.b32 p, %1, 0; @p mbarrier.arrive.shared::cta.b64 _, [%0]; }" ::"r"(bar), "r"((int)p) : "memory");
}
__device__ __forceinline__ void mbar_arrive_cl(uint32_t bar, uint32_t off, bool p = true) {
  asm volatile("{ .reg .pred p, q; .reg .b32 a; setp.ne.b32 q, %2, 0; setp.ne.and.b32 p, %0, 0, q; add.u32 a, %0, %1; @p mbarrier.arrive.shared::cluster.b64 _, [a]; }"
               ::"r"(bar), "r"(off), "r"((int)p) : "memory");
}
__device__ __forceinline__ uint32_t mapa(uint32_t addr, uint32_t cta) {
  uint32_t r; asm("mapa.shared::cluster.u32 %0, %1, %2;" : "=r"(r) : "r"(addr), "r"(cta)); return r;
}
__device__ __forceinline__ void cluster_arrive() { asm volatile("barrier.cluster.arrive.relaxed.aligned;" ::: "memory"); }
__device__ __forceinline__ void cluster_wait() { asm volatile("barrier.cluster.wait.aligned;" ::: "memory"); }
__device__ __forceinline__ void watchdog(uint32_t& n) {
}
__device__ __forceinline__ void mbar_wait(uint32_t bar, uint32_t parity) {
  asm volatile("{\n.reg .pred p;\nWAIT_%=:\nmbarrier.try_wait.parity.shared::cta.b64 p, [%0], %1;\n@!p bra WAIT_%=;\n}" ::"r"(bar), "r"(parity) : "memory");
}
__device__ __forceinline__ bool mbar_test(uint32_t bar, uint32_t parity) {
  uint32_t ok;
  asm volatile("{\n.reg .pred p;\nmbarrier.test_wait.parity.shared::cta.b64 p, [%1], %2;\nselp.u32 %0, 1, 0, p;\n}" : "=r"(ok) : "r"(bar), "r"(parity) : "memory");
  return ok;
}
__device__ __forceinline__ uint64_t l2_stream() {
  uint64_t f; asm("createpolicy.fractional.L2::evict_first.b64 %0, 1.0;" : "=l"(f)); return f;
}
__device__ __forceinline__ void tma2d(uint32_t dst, const CUtensorMap* m, int c0, int c1, uint32_t bar) {
  asm volatile("cp.async.bulk.tensor.2d.shared::cluster.global.mbarrier::complete_tx::bytes.L2::cache_hint [%0], [%1, {%3, %4}], [%2], %5;"
               ::"r"(dst), "l"(m), "r"(bar), "r"(c0), "r"(c1), "l"(l2_stream()) : "memory");
}
__device__ __forceinline__ void bulk_load(uint32_t dst, const void* src, uint32_t bytes, uint32_t bar) {
  asm volatile("cp.async.bulk.shared::cluster.global.mbarrier::complete_tx::bytes [%0], [%1], %2, [%3];" ::"r"(dst), "l"(src), "r"(bytes), "r"(bar) : "memory");
}
__device__ __forceinline__ void bulk_load_stream(uint32_t dst, const void* src, uint32_t bytes, uint32_t bar) {
  asm volatile("cp.async.bulk.shared::cluster.global.mbarrier::complete_tx::bytes.L2::cache_hint [%0], [%1], %2, [%3], %4;"
               ::"r"(dst), "l"(src), "r"(bytes), "r"(bar), "l"(l2_stream()) : "memory");
}
__device__ __forceinline__ void tma2d_store(const CUtensorMap* m, uint32_t src, int c0, int c1) {
  asm volatile("cp.async.bulk.tensor.2d.global.shared::cta.bulk_group [%0, {%2, %3}], [%1];" ::"l"(m), "r"(src), "r"(c0), "r"(c1) : "memory");
}
__device__ __forceinline__ void bulk_store(void* dst, uint32_t src, uint32_t bytes) {
  asm volatile("cp.async.bulk.global.shared::cta.bulk_group [%0], [%1], %2;" ::"l"(dst), "r"(src), "r"(bytes) : "memory");
}
__device__ __forceinline__ uint32_t unit_of(uint32_t table, uint32_t i) { return ((table >> (i * 4)) & 15) * UNIT; }
__device__ __forceinline__ void tma3d(uint32_t dst, const CUtensorMap* m, int c0, int c1, int c2, uint32_t bar) {
  asm volatile("cp.async.bulk.tensor.3d.shared::cluster.global.mbarrier::complete_tx::bytes.L2::cache_hint [%0], [%1, {%3, %4, %5}], [%2], %6;"
               ::"r"(dst), "l"(m), "r"(bar), "r"(c0), "r"(c1), "r"(c2), "l"(l2_stream()) : "memory");
}
template <bool STREAM>
__device__ __forceinline__ void tma3d_mc(uint32_t dst, const CUtensorMap* m, int c0, int c1, int c2, uint32_t bar) {
  if (STREAM)
    asm volatile("cp.async.bulk.tensor.3d.shared::cluster.global.mbarrier::complete_tx::bytes.multicast::cluster.L2::cache_hint [%0], [%1, {%3, %4, %5}], [%2], %6, %7;"
                 ::"r"(dst), "l"(m), "r"(bar), "r"(c0), "r"(c1), "r"(c2), "h"((uint16_t)3), "l"(l2_stream()) : "memory");
  else
    asm volatile("cp.async.bulk.tensor.3d.shared::cluster.global.mbarrier::complete_tx::bytes.multicast::cluster [%0], [%1, {%3, %4, %5}], [%2], %6;"
                 ::"r"(dst), "l"(m), "r"(bar), "r"(c0), "r"(c1), "r"(c2), "h"((uint16_t)3) : "memory");
}
__device__ __forceinline__ void prefetch_map(const CUtensorMap* m) {
  asm volatile("prefetch.tensormap [%0];" ::"l"(m) : "memory");
}
__device__ __forceinline__ void fence_async() { asm volatile("fence.proxy.async.global;" ::: "memory"); }
__device__ __forceinline__ void fence_async_smem() { asm volatile("fence.proxy.async.shared::cta;" ::: "memory"); }
__device__ __forceinline__ void bar_sync(int id, int n) { asm volatile("bar.sync %0, %1;" ::"r"(id), "r"(n) : "memory"); }
__device__ __forceinline__ void bar_arrive(int id, int n) { asm volatile("bar.arrive %0, %1;" ::"r"(id), "r"(n) : "memory"); }
__device__ __forceinline__ void wg_fence() { asm volatile("wgmma.fence.sync.aligned;" ::: "memory"); }
__device__ __forceinline__ void wg_commit() { asm volatile("wgmma.commit_group.sync.aligned;" ::: "memory"); }
template <int N> __device__ __forceinline__ void wg_wait() { asm volatile("wgmma.wait_group.sync.aligned %0;" ::"n"(N) : "memory"); }
__device__ __forceinline__ uint64_t make_desc(uint32_t addr, uint32_t lbo, uint32_t sbo) {
  return (uint64_t)((addr & 0x3FFFF) >> 4) | ((uint64_t)(lbo >> 4) << 16) | ((uint64_t)(sbo >> 4) << 32) | (1ull << 62);
}
__device__ __forceinline__ uint32_t ld_relaxed(const uint32_t* p) {
  uint32_t v; asm volatile("ld.relaxed.gpu.global.u32 %0, [%1];" : "=r"(v) : "l"(p) : "memory"); return v;
}
__device__ __forceinline__ uint32_t ld_acquire(const uint32_t* p) {
  uint32_t v; asm volatile("ld.acquire.gpu.global.u32 %0, [%1];" : "=r"(v) : "l"(p) : "memory"); return v;
}
__device__ __forceinline__ uint4 ld_relaxed4(const uint32_t* p) {
  uint4 v; asm volatile("ld.relaxed.gpu.global.v4.u32 {%0,%1,%2,%3}, [%4];" : "=r"(v.x), "=r"(v.y), "=r"(v.z), "=r"(v.w) : "l"(p) : "memory"); return v;
}
__device__ __forceinline__ uint2 ld_relaxed2(const uint32_t* p) {
  uint2 v; asm volatile("ld.relaxed.gpu.global.v2.u32 {%0,%1}, [%2];" : "=r"(v.x), "=r"(v.y) : "l"(p) : "memory"); return v;
}
__device__ __forceinline__ void st_relaxed(uint32_t* p, uint32_t v) {
  asm volatile("st.relaxed.gpu.global.u32 [%0], %1;" ::"l"(p), "r"(v) : "memory");
}
__device__ __forceinline__ void st_relaxed2(uint32_t* p, uint32_t a, uint32_t b) {
  asm volatile("st.relaxed.gpu.global.v2.u32 [%0], {%1,%2};" ::"l"(p), "r"(a), "r"(b) : "memory");
}
__device__ __forceinline__ void st_relaxed4(uint32_t* p, uint32_t a, uint32_t b, uint32_t c, uint32_t d) {
  asm volatile("st.relaxed.gpu.global.v4.u32 [%0], {%1,%2,%3,%4};" ::"l"(p), "r"(a), "r"(b), "r"(c), "r"(d) : "memory");
}
__device__ __forceinline__ void st_b128(uint32_t* p, uint32_t a, uint32_t b, uint32_t c, uint32_t d) {
  asm volatile("{ .reg .b64 u, v; .reg .b128 w; mov.b64 u, {%1, %2}; mov.b64 v, {%3, %4}; mov.b128 w, {u, v}; st.relaxed.gpu.global.b128 [%0], w; }"
               ::"l"(p), "r"(a), "r"(b), "r"(c), "r"(d) : "memory");
}
__device__ __forceinline__ uint4 ld_b128(const uint32_t* p) {
  uint4 r;
  asm volatile("{ .reg .b64 u, v; .reg .b128 w; ld.relaxed.gpu.global.b128 w, [%4]; mov.b128 {u, v}, w; mov.b64 {%0, %1}, u; mov.b64 {%2, %3}, v; }"
               : "=r"(r.x), "=r"(r.y), "=r"(r.z), "=r"(r.w) : "l"(p) : "memory");
  return r;
}
__device__ __forceinline__ void st_pairs(uint32_t* p, uint32_t a, uint32_t b, uint32_t tag) {
  asm volatile("{ .reg .b64 u, v; mov.b64 u, {%1, %3}; mov.b64 v, {%2, %3}; st.relaxed.gpu.global.v2.b64 [%0], {u, v}; }"
               ::"l"(p), "r"(a), "r"(b), "r"(tag) : "memory");
}
__device__ __forceinline__ uint4 ld_pairs(const uint32_t* p) {
  uint4 v;
  asm volatile("{ .reg .b64 u, v; ld.relaxed.gpu.global.v2.b64 {u, v}, [%4]; mov.b64 {%0, %1}, u; mov.b64 {%2, %3}, v; }"
               : "=r"(v.x), "=r"(v.y), "=r"(v.z), "=r"(v.w) : "l"(p) : "memory");
  return v;
}
__device__ __forceinline__ uint2 ld_pair(const uint32_t* p) {
  uint2 v;
  asm volatile("{ .reg .b64 u; ld.relaxed.gpu.global.b64 u, [%2]; mov.b64 {%0, %1}, u; }" : "=r"(v.x), "=r"(v.y) : "l"(p) : "memory");
  return v;
}
__device__ __forceinline__ void red_release(uint32_t* p, uint32_t v) {
  asm volatile("red.release.gpu.global.add.u32 [%0], %1;" ::"l"(p), "r"(v) : "memory");
}
__device__ __forceinline__ uint32_t ldg_nc1(const void* p) {
  uint32_t v;
  asm volatile("ld.global.nc.u32 %0, [%1];" : "=r"(v) : "l"(p));
  return v;
}
__device__ __forceinline__ uint4 ldg_nc4(const void* p) {
  uint4 v; asm volatile("ld.global.nc.L1::no_allocate.v4.u32 {%0,%1,%2,%3}, [%4];" : "=r"(v.x), "=r"(v.y), "=r"(v.z), "=r"(v.w) : "l"(p)); return v;
}
__device__ __forceinline__ uint4 ldg_stream4(const void* p) {
  uint4 v;
  asm volatile("ld.global.nc.L1::no_allocate.L2::cache_hint.v4.u32 {%0,%1,%2,%3}, [%4], %5;" : "=r"(v.x), "=r"(v.y), "=r"(v.z), "=r"(v.w) : "l"(p), "l"(l2_stream()));
  return v;
}
__device__ __forceinline__ void stg4(void* p, uint4 v) {
  asm volatile("st.global.v4.u32 [%0], {%1,%2,%3,%4};" ::"l"(p), "r"(v.x), "r"(v.y), "r"(v.z), "r"(v.w) : "memory");
}
__device__ __forceinline__ void wait_counter(const uint32_t* p, uint32_t target) {
  uint32_t n = 0;
  while (__any_sync(0xffffffffu, (int)(ld_acquire(p) - target) < 0)) { watchdog(n); }
}
__device__ __forceinline__ uint32_t tagf(float v, uint32_t tag) { return (__float_as_uint(v) & ~3u) | tag; }
__device__ __forceinline__ bool tag_ok(uint4 v, uint32_t tag) { return (((v.x ^ tag) | (v.y ^ tag) | (v.z ^ tag) | (v.w ^ tag)) & 3u) == 0; }
__device__ __forceinline__ float untag_sum(uint32_t a, uint32_t b) { return __uint_as_float(a & ~3u) + __uint_as_float(b & ~3u); }
__device__ __forceinline__ uint4 poll4(const uint32_t* p, uint32_t tag) {
  uint4 v = ld_relaxed4(p);
  uint32_t n = 0;
  while (!__all_sync(0xffffffffu, tag_ok(v, tag))) { v = ld_relaxed4(p); watchdog(n); }
  return v;
}
__device__ __forceinline__ float bf_lo(uint32_t v) { return __uint_as_float(v << 16); }
__device__ __forceinline__ float bf_hi(uint32_t v) { return __uint_as_float(v & 0xffff0000u); }
__device__ __forceinline__ uint32_t pack_bf(float lo, float hi) {
  uint32_t r; asm("cvt.rn.bf16x2.f32 %0, %1, %2;" : "=r"(r) : "f"(hi), "f"(lo)); return r;
}
__device__ __forceinline__ float rbf(float v) { return __uint_as_float(pack_bf(0.f, v) & 0xffff0000u); }
__device__ __forceinline__ uint32_t hmul2(uint32_t a, uint32_t b) {
  uint32_t r; asm("mul.rn.bf16x2 %0, %1, %2;" : "=r"(r) : "r"(a), "r"(b)); return r;
}
__device__ __forceinline__ uint32_t hadd2(uint32_t a, uint32_t b) {
  uint32_t r; asm("add.rn.bf16x2 %0, %1, %2;" : "=r"(r) : "r"(a), "r"(b)); return r;
}
__device__ __forceinline__ uint32_t hsub2(uint32_t a, uint32_t b) {
  uint32_t r; asm("sub.rn.bf16x2 %0, %1, %2;" : "=r"(r) : "r"(a), "r"(b)); return r;
}
__device__ __forceinline__ uint32_t hmax2(uint32_t a, uint32_t b) {
  uint32_t r; asm("max.bf16x2 %0, %1, %2;" : "=r"(r) : "r"(a), "r"(b)); return r;
}
__device__ __forceinline__ float rcp(float x) { float r; asm("rcp.approx.ftz.f32 %0, %1;" : "=f"(r) : "f"(x)); return r; }
__device__ __forceinline__ float ex2(float x) { float r; asm("ex2.approx.ftz.f32 %0, %1;" : "=f"(r) : "f"(x)); return r; }
__device__ __forceinline__ void stmatrix4(uint32_t addr, uint32_t a, uint32_t b, uint32_t c, uint32_t d) {
  asm volatile("stmatrix.sync.aligned.m8n8.x4.shared.b16 [%0], {%1,%2,%3,%4};" ::"r"(addr), "r"(a), "r"(b), "r"(c), "r"(d) : "memory");
}
__device__ __forceinline__ void ldmatrix4(uint32_t addr, uint32_t& a, uint32_t& b, uint32_t& c, uint32_t& d) {
  asm volatile("ldmatrix.sync.aligned.m8n8.x4.shared.b16 {%0,%1,%2,%3}, [%4];" : "=r"(a), "=r"(b), "=r"(c), "=r"(d) : "r"(addr) : "memory");
}
__device__ __forceinline__ void ldmatrix4t(uint32_t addr, uint32_t& a, uint32_t& b, uint32_t& c, uint32_t& d) {
  asm volatile("ldmatrix.sync.aligned.m8n8.x4.trans.shared.b16 {%0,%1,%2,%3}, [%4];" : "=r"(a), "=r"(b), "=r"(c), "=r"(d) : "r"(addr) : "memory");
}
__device__ __forceinline__ void mma16816(float (&d)[4], uint32_t a0, uint32_t a1, uint32_t a2, uint32_t a3, uint32_t b0, uint32_t b1) {
  asm volatile("mma.sync.aligned.m16n8k16.row.col.f32.bf16.bf16.f32 {%0,%1,%2,%3}, {%4,%5,%6,%7}, {%8,%9}, {%0,%1,%2,%3};"
               : "+f"(d[0]), "+f"(d[1]), "+f"(d[2]), "+f"(d[3]) : "r"(a0), "r"(a1), "r"(a2), "r"(a3), "r"(b0), "r"(b1));
}
__device__ __forceinline__ void sts1(uint32_t a, uint32_t v) { asm volatile("st.shared.u32 [%0], %1;" ::"r"(a), "r"(v) : "memory"); }
__device__ __forceinline__ uint4 lds4(uint32_t a) {
  uint4 v; asm volatile("ld.shared.v4.u32 {%0,%1,%2,%3}, [%4];" : "=r"(v.x), "=r"(v.y), "=r"(v.z), "=r"(v.w) : "r"(a) : "memory"); return v;
}
__device__ __forceinline__ uint2 lds2(uint32_t a) {
  uint2 v; asm volatile("ld.shared.v2.u32 {%0,%1}, [%2];" : "=r"(v.x), "=r"(v.y) : "r"(a) : "memory"); return v;
}
__device__ __forceinline__ uint32_t lds1(uint32_t a) {
  uint32_t v; asm volatile("ld.shared.u32 %0, [%1];" : "=r"(v) : "r"(a) : "memory"); return v;
}
__device__ __forceinline__ void sts2(uint32_t a, uint32_t x, uint32_t y) { asm volatile("st.shared.v2.u32 [%0], {%1,%2};" ::"r"(a), "r"(x), "r"(y) : "memory"); }
__device__ __forceinline__ void sts4(uint32_t a, uint4 v) {
  asm volatile("st.shared.v4.u32 [%0], {%1,%2,%3,%4};" ::"r"(a), "r"(v.x), "r"(v.y), "r"(v.z), "r"(v.w) : "memory");
}
__device__ __forceinline__ float silu_f(float v) { return __fdividef(v, 1.f + __expf(-v)); }
__device__ __forceinline__ uint32_t hfma2(uint32_t a, uint32_t b, uint32_t c) {
  uint32_t r; asm("fma.rn.bf16x2 %0, %1, %2, %3;" : "=r"(r) : "r"(a), "r"(b), "r"(c)); return r;
}
__device__ __forceinline__ void split_inv(float sd, uint32_t& ih, uint32_t& il) {
  const float inv = rcp(sd);
  ih = pack_bf(inv, inv);
  const float lo = inv - bf_lo(ih);
  il = pack_bf(lo, lo);
}
__device__ __forceinline__ uint32_t ln_norm(uint32_t x, uint32_t mean2, uint32_t ih, uint32_t il) {
  const uint32_t d = hsub2(x, mean2);
  return hfma2(d, ih, hmul2(d, il));
}
__device__ __forceinline__ uint32_t modul(uint32_t n, uint32_t c1, uint32_t sh) { return hadd2(hmul2(n, c1), sh); }
__device__ __forceinline__ uint32_t ln_mod(uint32_t x, uint32_t mean2, uint32_t ih, uint32_t il, uint32_t c1, uint32_t sh) {
  return modul(ln_norm(x, mean2, ih, il), c1, sh);
}

#define R8(a, i) "+f"(a[i]), "+f"(a[i + 1]), "+f"(a[i + 2]), "+f"(a[i + 3]), "+f"(a[i + 4]), "+f"(a[i + 5]), "+f"(a[i + 6]), "+f"(a[i + 7])
#define D64 "{%0,%1,%2,%3,%4,%5,%6,%7,%8,%9,%10,%11,%12,%13,%14,%15,%16,%17,%18,%19,%20,%21,%22,%23,%24,%25,%26,%27,%28,%29,%30,%31," \
            "%32,%33,%34,%35,%36,%37,%38,%39,%40,%41,%42,%43,%44,%45,%46,%47,%48,%49,%50,%51,%52,%53,%54,%55,%56,%57,%58,%59,%60,%61,%62,%63}"
template <int TB>
__device__ __forceinline__ void mma_ss(float (&d)[64], uint64_t da, uint64_t db, int sc) {
  asm volatile("{\n.reg .pred p;\nsetp.ne.b32 p, %66, 0;\n"
               "wgmma.mma_async.sync.aligned.m64n128k16.f32.bf16.bf16 " D64 ", %64, %65, p, 1, 1, 0, %67;\n}"
               : R8(d, 0), R8(d, 8), R8(d, 16), R8(d, 24), R8(d, 32), R8(d, 40), R8(d, 48), R8(d, 56)
               : "l"(da), "l"(db), "r"(sc), "n"(TB));
}
template <int TB>
__device__ __forceinline__ void mma_rs(float (&d)[64], uint32_t a0, uint32_t a1, uint32_t a2, uint32_t a3, uint64_t db, int sc) {
  asm volatile("{\n.reg .pred p;\nsetp.ne.b32 p, %69, 0;\n"
               "wgmma.mma_async.sync.aligned.m64n128k16.f32.bf16.bf16 " D64 ", {%64,%65,%66,%67}, %68, p, 1, 1, %70;\n}"
               : R8(d, 0), R8(d, 8), R8(d, 16), R8(d, 24), R8(d, 32), R8(d, 40), R8(d, 48), R8(d, 56)
               : "r"(a0), "r"(a1), "r"(a2), "r"(a3), "l"(db), "r"(sc), "n"(TB));
}
#define D128 "{%0,%1,%2,%3,%4,%5,%6,%7,%8,%9,%10,%11,%12,%13,%14,%15,%16,%17,%18,%19,%20,%21,%22,%23,%24,%25,%26,%27,%28,%29,%30,%31," \
             "%32,%33,%34,%35,%36,%37,%38,%39,%40,%41,%42,%43,%44,%45,%46,%47,%48,%49,%50,%51,%52,%53,%54,%55,%56,%57,%58,%59,%60,%61,%62,%63," \
             "%64,%65,%66,%67,%68,%69,%70,%71,%72,%73,%74,%75,%76,%77,%78,%79,%80,%81,%82,%83,%84,%85,%86,%87,%88,%89,%90,%91,%92,%93,%94,%95," \
             "%96,%97,%98,%99,%100,%101,%102,%103,%104,%105,%106,%107,%108,%109,%110,%111,%112,%113,%114,%115,%116,%117,%118,%119,%120,%121,%122,%123,%124,%125,%126,%127}"
#define R128(d, e) R8(d, 0), R8(d, 8), R8(d, 16), R8(d, 24), R8(d, 32), R8(d, 40), R8(d, 48), R8(d, 56), \
                   R8(e, 0), R8(e, 8), R8(e, 16), R8(e, 24), R8(e, 32), R8(e, 40), R8(e, 48), R8(e, 56)
__device__ __forceinline__ void mma256_ss(float (&d)[64], float (&e)[64], uint64_t da, uint64_t db, int sc) {
  asm volatile("{\n.reg .pred p;\nsetp.ne.b32 p, %130, 0;\n"
               "wgmma.mma_async.sync.aligned.m64n256k16.f32.bf16.bf16 " D128 ", %128, %129, p, 1, 1, 0, 1;\n}"
               : R128(d, e) : "l"(da), "l"(db), "r"(sc));
}
__device__ __forceinline__ void mma256_rs(float (&d)[64], float (&e)[64], uint32_t a0, uint32_t a1, uint32_t a2, uint32_t a3, uint64_t db) {
  asm volatile("{\n.reg .pred p;\nsetp.ne.b32 p, 1, 0;\n"
               "wgmma.mma_async.sync.aligned.m64n256k16.f32.bf16.bf16 " D128 ", {%128,%129,%130,%131}, %132, p, 1, 1, 1;\n}"
               : R128(d, e) : "r"(a0), "r"(a1), "r"(a2), "r"(a3), "l"(db));
}
template <int N> __device__ __forceinline__ void keep(float (&a)[N]) {
#pragma unroll
  for (int i = 0; i < N; i++) asm volatile("" : "+f"(a[i])::"memory");
}
template <int N> __device__ __forceinline__ void keep(uint32_t (&a)[N]) {
#pragma unroll
  for (int i = 0; i < N; i++) asm volatile("" : "+r"(a[i])::"memory");
}

#define STAMP(idx) do {} while (0)
#define PROF(grp, cond, idx) do {} while (0)

constexpr float SCL2 = 1.4426950408889634f * 0.08838834764831845f;

__device__ __forceinline__ void pack_p(const float (&s)[64], uint32_t (&p)[32]) {
#pragma unroll
  for (int i = 0; i < 32; i++) p[i] = pack_bf(s[2 * i], s[2 * i + 1]);
}

__device__ __forceinline__ void issue_qk(float (&s)[64], uint32_t q0, uint32_t q1, uint32_t kslot) {
  const uint64_t db = make_desc(kslot, 16, 1024), da0 = make_desc(q0, 16, 1024), da1 = make_desc(q1, 16, 1024);
#pragma unroll
  for (int kk = 0; kk < 8; kk++) mma_ss<0>(s, (kk < 4 ? da0 : da1) + (kk & 3) * 2, db + (kk >> 2) * 1024 + (kk & 3) * 2, kk != 0);
}
__device__ __forceinline__ void issue_pv(float (&o)[64], uint32_t (&p)[32], uint32_t vslot, int acc) {
  uint64_t db = make_desc(vslot, 16384, 1024);
#pragma unroll
  for (int kk = 0; kk < 8; kk++)
    mma_rs<1>(o, p[4 * kk], p[4 * kk + 1], p[4 * kk + 2], p[4 * kk + 3], db + kk * 128, kk == 0 ? acc : 1);
}

template <int H>
__device__ __forceinline__ void store_chunk(const float (&a)[64], uint32_t addr) {
#pragma unroll
  for (int i = 8 * H; i < 8 * H + 8; i += 2)
    stmatrix4(addr ^ ((i & 7) << 4), pack_bf(a[4 * i], a[4 * i + 1]), pack_bf(a[4 * i + 2], a[4 * i + 3]),
              pack_bf(a[4 * i + 4], a[4 * i + 5]), pack_bf(a[4 * i + 6], a[4 * i + 7]));
}
template <int H>
__device__ __forceinline__ void store_chunk(const float (&a)[64], float i0, float i1, uint32_t addr) {
#pragma unroll
  for (int i = 8 * H; i < 8 * H + 8; i += 2)
    stmatrix4(addr ^ ((i & 7) << 4), pack_bf(a[4 * i] * i0, a[4 * i + 1] * i0), pack_bf(a[4 * i + 2] * i1, a[4 * i + 3] * i1),
              pack_bf(a[4 * i + 4] * i0, a[4 * i + 5] * i0), pack_bf(a[4 * i + 6] * i1, a[4 * i + 7] * i1));
}
__device__ __forceinline__ float inv_quad_sum(float l) {
  l += __shfl_xor_sync(0xffffffffu, l, 1);
  l += __shfl_xor_sync(0xffffffffu, l, 2);
  return rcp(l);
}

__device__ __forceinline__ void ln_scalars(float mean, float var, float& mb, float& sd) {
  mb = rbf(mean);
  float r; asm("sqrt.approx.ftz.f32 %0, %1;" : "=f"(r) : "f"(rbf(rbf(var) + 1e-5f)));
  sd = rbf(r);
}

__global__ void __cluster_dims__(2, 1, 1) __launch_bounds__(384, 1) fused_kernel(const __grid_constant__ Maps maps, const Ptrs P) {
  extern __shared__ __align__(1024) uint8_t smem_raw[];
  const uint32_t base = smem_u32(smem_raw);
  const int tid = threadIdx.x, lane = tid & 31;
  const int warp = __shfl_sync(0xffffffffu, tid >> 5, 0);
  const int b = blockIdx.x;
  PROF(31, tid == 0, 0);

  if (b >= NMAIN) {
    float* sc = reinterpret_cast<float*>(smem_raw);
    float* red = sc + DM;
    for (int k = tid; k < DM; k += 384) sc[k] = rbf(silu_f(__bfloat162float(P.c[k])));
    __syncthreads();
    if (tid < 256) {
      const int col = 2048 + (b - NMAIN) * 1024 + (tid & 127) * 8, r0 = (tid >> 7) * 512;
      float acc[8];
#pragma unroll
      for (int e = 0; e < 8; e++) acc[e] = 0.f;
#pragma unroll 1
      for (int r = r0; r < r0 + 512; r += HU) {
        uint4 w[HU];
#pragma unroll
        for (int u = 0; u < HU; u++) w[u] = ldg_stream4(P.w_mod + (size_t)(r + u) * NMOD + col);
#pragma unroll
        for (int u = 0; u < HU; u++) {
          float s = sc[r + u];
          acc[0] += s * bf_lo(w[u].x); acc[1] += s * bf_hi(w[u].x); acc[2] += s * bf_lo(w[u].y); acc[3] += s * bf_hi(w[u].y);
          acc[4] += s * bf_lo(w[u].z); acc[5] += s * bf_hi(w[u].z); acc[6] += s * bf_lo(w[u].w); acc[7] += s * bf_hi(w[u].w);
        }
      }
      if (tid >= 128) {
#pragma unroll
        for (int e = 0; e < 8; e++) red[(tid & 127) * 8 + e] = acc[e];
      }
      const uint32_t tag = ld_relaxed(&g_epoch) % 3 + 1;
      bar_sync(1, 256);
      if (tid < 128) {
        uint32_t o[8];
#pragma unroll
        for (int e = 0; e < 8; e++) o[e] = __float_as_uint(rbf(acc[e] + red[tid * 8 + e])) | tag;
        st_relaxed4(g_mod + col, o[0], o[1], o[2], o[3]);
        st_relaxed4(g_mod + col + 4, o[4], o[5], o[6], o[7]);
        const uint4 wr = ldg_nc4(P.w_r + tid * 8);
        const uint32_t wv[4] = {wr.x, wr.y, wr.z, wr.w};
        float dsum = 0.f;
#pragma unroll
        for (int e = 0; e < 8; e++) {
          const float m = bf_hi(o[e]);
          dsum += (b == NMAIN + 2 ? rbf(1.f + m) : m) * ((e & 1) ? bf_hi(wv[e >> 1]) : bf_lo(wv[e >> 1]));
        }
#pragma unroll
        for (int k = 16; k > 0; k >>= 1) dsum += __shfl_xor_sync(0xffffffffu, dsum, k);
        if (lane == 0) st_relaxed(g_mod + (b - NMAIN) * 4 + warp, tagf(dsum, tag));
      }
    }
    PROF(2, tid == 0, 1);
    return;
  }

  const int rank = b & 1;
  const int rb = ((b >> 4) << 1) | rank, cj = (b >> 1) & 7;
  const uint32_t bfull = base + OFF_BAR, bempty = bfull + NSLOT * 8;
  const uint32_t gfull = bempty + NSLOT * 8, gempty = gfull + 32;
  const uint32_t bar_ofull = gempty + 32;
  const uint32_t bar_ofree = bar_ofull + 32;
  const uint32_t bar_par = bar_ofree + 32;
  const uint32_t bar_mod = bar_par + 8;
  const uint32_t bar_pread = bar_mod + 8;
  const uint32_t bar_xres = bar_pread + 8;
  const uint32_t bar_ring = bar_xres + 8;
  const uint32_t bar_box = bar_ring + 24;
  const uint32_t bar_go = bar_box + 96;
  const uint32_t bar_go2 = bar_go + 16;
  const uint32_t bar_cnt = bar_go + 24;
  const uint32_t xfull = bar_go + 40, xempty = xfull + 32;
  const uint32_t bar_hw = xempty + 32, bar_hx = bar_hw + 8;
  const uint32_t bar_hpub = bar_hx + 16;
  const uint32_t bar_win = bar_hpub + 16;
  const uint32_t bar_rx = bar_win + 8;
  const uint32_t bar_sel = bar_rx + 8;
  const uint32_t bar_gate = bar_sel + 8;
  const uint32_t bar_rel = bar_gate + 8;
  const uint32_t bar_od = bar_rel + 8;
  const uint32_t bar_res = bar_go + 8;
  const uint32_t stage = base + OFF_STAGE, par = base + OFF_PAR;

  if (warp == 8 && elect_one()) {
    for (int s = 0; s < NSLOT; s++) { mbar_init(bfull + s * 8, 1); mbar_init(bempty + s * 8, 16); }
    for (int s = 0; s < 4; s++) { mbar_init(gfull + s * 8, 1); mbar_init(gempty + s * 8, 16); mbar_init(xfull + s * 8, 1); mbar_init(xempty + s * 8, 8); mbar_init(bar_ofree + s * 8, 1); mbar_init(bar_ofull + s * 8, 128); }
    mbar_init(bar_par, 64); mbar_init(bar_mod, 256); mbar_init(bar_pread, 2); mbar_init(bar_xres, 1);
    mbar_init(bar_ring, 8); mbar_init(bar_ring + 8, 8); mbar_init(bar_ring + 16, 8);
    mbar_init(bar_go, 1); mbar_init(bar_go2, 1); mbar_init(bar_cnt, 1); mbar_init(bar_cnt + 8, 1); mbar_init(bar_hpub, 8); mbar_init(bar_hpub + 8, 8); mbar_init(bar_res, 1); mbar_init(bar_win, 1); mbar_init(bar_rx, 1); mbar_init(bar_sel, 64); mbar_init(bar_gate, 8); mbar_init(bar_rel, 8); mbar_init(bar_od, 1);
    for (int s = 0; s < 12; s++) mbar_init(bar_box + s * 8, 1);
    asm volatile("fence.mbarrier_init.release.cluster;" ::: "memory");
    prefetch_map(&maps.x); prefetch_map(&maps.wq); prefetch_map(&maps.k); prefetch_map(&maps.v);
  }
  if (warp == 9 && elect_one()) {
    mbar_init(bar_hw, 1); mbar_init(bar_hx, 1); mbar_init(bar_hx + 8, 1);
    asm volatile("fence.mbarrier_init.release.cluster;" ::: "memory");
    mbar_expect_tx(bar_hw, 32768);
    mbar_expect_tx(bar_hx, 16384);
    mbar_expect_tx(bar_hx + 8, 16384);
    const __nv_bfloat16* xs = P.x + (size_t)(rb * 128 + cj * 16) * DM;
    bulk_load(base + 2 * GST_BYTES, xs, 16384, bar_hx);
    tma2d(stage, &maps.wm, (b >> 1) * 32, rank * 512, bar_hw);
    tma2d(stage + 16384, &maps.wm, (b >> 1) * 32, rank * 512 + 256, bar_hw);
    bulk_load(base + 3 * GST_BYTES, xs + 8 * DM, 16384, bar_hx + 8);
  }
  cluster_arrive();

  if (warp >= 8) {
    asm volatile("setmaxnreg.dec.sync.aligned.u32 40;");
    if (warp < 10) bar_arrive(1, 320);
    const uint32_t epoch = ld_relaxed(&g_epoch);
    cluster_wait();
    if (warp == 8) {
      const int kvrow = (cj >> 1) * SK + (SK - WIN);
      int wch = cj * 8 + rank * 2;
#pragma unroll 1
      for (int ps = 0; ps < 3; ps++) {
        const CUtensorMap* mw = ps == 2 ? &maps.wo : &maps.wq;
        const uint32_t xt = ps == 1 ? XT1 : XT2, wt = ps == 0 ? WT0 : (ps == 1 ? WT1 : WT2);
        const int nst = ps == 2 ? 32 : 16;
#pragma unroll 1
        for (int i = 0; i < nst; i++) {
          const uint32_t bf = gfull + (i & 3) * 8;
          const int kt = ps == 2 ? (((cj & 1) * 4 + ((i >> 1) & 3)) * 4 + (i >> 3)) * 2 + (i & 1) : (i + (ps ? 0 : b & 14)) & 15;
          const uint32_t wd = base + unit_of(wt, i & 3) + rank * UNIT, xd = base + unit_of(xt, i & 3);
          const uint8_t* xs = g_act + (uint32_t)(rb * 80 + (ps - 1) * 16 + kt) * UNIT;
          if (ps == 0 && i == HD) mbar_wait(bar_mod, 0);
          const bool xfirst = ps && i < 2;
          if (ps == 2 && i == 0) mbar_wait(bar_ofree + 24, 0);
          if (i == 0) fence_async();
          mbar_wait(gempty + (i & 3) * 8, ((i >> 2) & 1) ^ 1);
          if (elect_one()) {
            mbar_expect_tx(bf, ps ? GST_BYTES : 2 * UNIT);
            if (xfirst) bulk_load_stream(xd, xs, UNIT, bf);
          }
          if (ps && i < 4) mbar_wait(bempty + i * 8, 1);
          if (elect_one()) tma3d_mc<true>(wd, mw, 0, (i == 31 ? kt ^ (rank * 32) : kt) * 64, i == 31 ? cj * 2 : wch, bf);
          if (ps) {
            if (i == 16 || i == 24) { mbar_wait(bar_cnt + i - 16, 0); fence_async(); }
            if (i == RES0) mbar_wait(bar_res, 0);
            if (i == 2) mbar_wait(bar_ofree + (ps - 1) * 16, 0);
            if (elect_one()) {
              if (i == 31) bulk_load(xd, xs, UNIT, bf); else if (!xfirst) bulk_load_stream(xd, xs, UNIT, bf);
              mbar_arrive_pred(bar_go, i == GOST - 1);
              mbar_arrive_pred(bar_od, i == ODS);
              if (i == RES0) mbar_expect_tx(bar_xres, 32768);
              if (i == RES0 || i == RES1) tma2d(base + OFF_RES + (i == RES1) * UNIT, &maps.x, cj * 128 + (i == RES1) * 64, rb * 128, bar_xres);
            }
          }
        }
        if (ps == 2) break;
        wch = ps ? ((wch >> 3) ^ rank) * 2 : wch + 4;
#pragma unroll 1
        for (int u = 0; u < 16; u++) {
          const bool isk = (u == 0) || ((u & 1) && u < 15);
          const int blk = (isk ? (u + 1) >> 1 : (u == 15 ? 7 : (u >> 1) - 1)) & 3;
          const uint32_t sl = base + unit_of(ps ? AT1 : AT0, u & 3) + rank * UNIT, bf = bfull + (u & 3) * 8;
          if (u < 4) mbar_wait(gempty + ((u + 1) >> 1) * 8, 1);
          mbar_wait(bempty + (u & 3) * 8, ((u >> 2) & 1) ^ 1);
          if (elect_one()) {
            mbar_arrive_pred(bar_go2, ps && u == PG0);
            mbar_expect_tx(bf, SLOT_BYTES);
            tma3d_mc<false>(sl, isk ? &maps.k : &maps.v, 0, kvrow + blk * 128, rank, bf);
          }
        }
      }
      if (elect_one()) mbar_expect_tx(bar_rx, UNIT);
      mbar_wait(bar_rel, 0);
      if (elect_one()) {
        bulk_load_stream(base + UNIT, g_act + (uint32_t)(rb * 80 + 16 + 63 - (cj & 1) * 32) * UNIT, UNIT, bar_rx);
      }
      if (b < NFFN) {
#pragma unroll 1
        for (int u = 0; u < 12; u++) {
          const uint32_t dst = base + unit_of(u < 4 ? FT_G : (u < 8 ? FT_U : FT_D), u & 3);
          if (elect_one()) mbar_expect_tx(bar_box + u * 8, UNIT);
          if (u == FB0 || u == 2 || u == FB2) mbar_wait(bar_ring + (u == FB2 ? 16 : (u + 6) & 8), 0);
          if (u >= FPACE) mbar_wait(bar_box + (u - FPACE) * 8, 0);
          if (elect_one()) {
            if (u < 8) tma2d(dst, u < 4 ? &maps.wg : &maps.wu, b * 32, (u & 3) * 256, bar_box + u * 8);
            else tma3d(dst, &maps.wd, 0, b * 32, (u - 8) * 4, bar_box + u * 8);
          }
        }
      }
    } else if (warp == 9) {
      const uint32_t target = 8 * (epoch + 1);
      uint32_t hmask = 0;
#pragma unroll 1
      for (int i = 0; i < 16; i++) {
        if (i == HDX) mbar_wait(bar_mod, 0);
        const uint32_t need = i == 15 ? 0xffffu : 1u << ((2 * cj + i) & 15);
        if (i >= NRS && (hmask & need) != need) {
          uint32_t n = 0;
          do { hmask = __ballot_sync(0xffffffffu, ld_acquire(&g_cnt_h[rb * 32 + (lane & 15)]) == epoch + 1); watchdog(n); } while ((hmask & need) != need);
          PROF(1, lane == 0 && i == NRS, 26);
          fence_async();
        }
        mbar_wait(xempty + (i & 3) * 8, ((i >> 2) & 1) ^ 1);
        if (elect_one()) {
          mbar_expect_tx(xfull + (i & 3) * 8, UNIT);
          if (i < NRS) tma2d(base + (i & 3) * GST_BYTES, &maps.x, ((2 * cj + i) & 15) * 64, rb * 128, xfull + (i & 3) * 8);
          else bulk_load_stream(base + (i & 3) * GST_BYTES, g_act + (uint32_t)(rb * 80 + ((2 * cj + i) & 15)) * UNIT, UNIT, xfull + (i & 3) * 8);
        }
      }
      prefetch_map(&maps.wo);
#pragma unroll 1
      for (int t = 0; t < 4; t++) {
        if (t & 1) mbar_wait(bar_od, t >> 1);
#pragma unroll 1
        for (int p = 0; p < 32768 / OPS; p++) {
          const uint32_t w = p / (16384 / OPS), c = (p / (8192 / OPS)) & 1, off = w * 8192 + (p % (8192 / OPS)) * OPS;
          mbar_wait(bar_ofull + (t & 1) * 16 + w * 8, t >> 1);
          if (elect_one()) {
            bulk_store(g_act + (uint32_t)(rb * 80 + 16 + (cj * 4 + t) * 2 + c) * UNIT + off, base + unit_of(QT, 2 * t + c) + off, OPS);
            asm volatile("cp.async.bulk.commit_group;" ::: "memory");
            asm volatile("cp.async.bulk.wait_group.read %0;" ::"n"(OFL) : "memory");
          }
        }
        if (elect_one()) {
          asm volatile("cp.async.bulk.wait_group.read 0;" ::: "memory");
          mbar_arrive(t < 3 ? bar_ofree + t * 8 : bar_res);
          asm volatile("cp.async.bulk.wait_group 0;" ::: "memory");
          fence_async();
          red_release(&g_cnt_o[((rb * 4 + t) * 2 + (cj >> 2)) * 32], 2);
        }
        if (t) {
          wait_counter(&g_cnt_o[(rb * 8 + 2 * t + (cj & 1)) * 32], target);
          if (t & 1) wait_counter(&g_cnt_o[(rb * 8 + (t == 1 ? cj & 1 : 7 - (cj & 1))) * 32], target);
          if (elect_one()) mbar_arrive(t == 1 ? bar_ofree + 24 : bar_cnt + t * 8 - 16);
        }
      }
      PROF(2, lane == 0, 27);
      const uint32_t tag = epoch % 3 + 1;
      const uint32_t* inbox = g_cand + (lane & 15);
      mbar_wait(bar_ring + 16, 0);
      uint32_t c0 = ld_relaxed(inbox), n = 0;
#define CAND_STEP(cv)                                                                                        \
      {                                                                                                      \
        const bool valid = (cv & 3u) == tag, all = __all_sync(0xffffffffu, valid);                           \
        const uint32_t best = __reduce_max_sync(0xffffffffu, valid ? cv : 0u);                               \
        const uint32_t blk = __ffs(__ballot_sync(0xffffffffu, cv == best)) - 1;                              \
        if (best) sts2(par + PAR_CONST + 56, best, (blk << 7 | (~best >> 2 & 127)) | (all ? 0x1800 : 0x800)); \
        if (all) break;                                                                                      \
        cv = ld_relaxed(inbox);                                                                              \
      }
      while (true) { CAND_STEP(c0) watchdog(n); }
    } else {
      const int t2 = tid - 320;
      mbar_wait(bar_hpub + (warp & 1) * 8, 0);
      PROF(1, t2 == 0, 24);
#pragma unroll 1
      for (int c = 0; c < 8; c++) {
        const uint32_t off = (warp & 1) * UNIT + c * 2048 + lane * 16;
        uint8_t* dst = g_act + (uint32_t)(rb * 80 + cj * 2) * UNIT + off;
        const uint4 v0 = lds4(stage + off), v1 = lds4(stage + off + 512), v2 = lds4(stage + off + 1024), v3 = lds4(stage + off + 1536);
        stg4(dst, v0); stg4(dst + 512, v1); stg4(dst + 1024, v2); stg4(dst + 1536, v3);
      }
      __syncwarp();
      PROF(1, t2 == 0, 15);
      if (lane == 0) {
        mbar_arrive(bar_pread);
        red_release(&g_cnt_h[rb * 32 + cj * 2 + (warp & 1)], 1);
        PROF(1, t2 == 0, 25);
        prefetch_map(&maps.wg); prefetch_map(&maps.wu); prefetch_map(&maps.wd); prefetch_map(&maps.out);
      }
      __syncwarp();
      if (b < NFFN) {
        mbar_wait(bar_go2, 0);
        const __nv_bfloat16* pg = ((b & 1) ? P.w_up : P.w_gate) + (b >> 1) * 64 + (size_t)t2 * FF;
        const __nv_bfloat16* pd = P.w_down + (size_t)b * 32768 + t2 * 64;
        PROF(2, t2 == 0, 13);
#pragma unroll 1
        for (int i = 0; i < WN; i += WB) {
          uint32_t v[WB];
#pragma unroll
          for (int u = 0; u < WB; u++) {
            const int k = i + u;
            asm volatile("ld.global.cg.L2::128B.u32 %0, [%1];" : "=r"(v[u]) : "l"(k < 16 ? pg + (size_t)k * 64 * FF : pd + (k - 16) * 4096));
          }
#pragma unroll
          for (int u = 1; u < WB; u++) v[0] ^= v[u];
          sts1(par + PAR_SINK + t2 * 4, v[0]);
        }
        PROF(2, t2 == 0, 14);
      }
      const uint32_t tag = epoch % 3 + 1;
      mbar_wait(bar_go, 0);
      if (warp == 10) {
        const uint32_t* src = g_mod + 2 * DM + cj * 128 + lane * 4;
        const uint2 wr = *reinterpret_cast<const uint2*>(P.w_r + cj * 128 + lane * 4);
        uint4 vga, vsb, vcb, vgb;
        uint32_t n = 0;
        do {
          vga = ld_relaxed4(src); vsb = ld_relaxed4(src + DM); vcb = ld_relaxed4(src + 2 * DM); vgb = ld_relaxed4(src + 3 * DM);
          watchdog(n);
        } while (!__all_sync(0xffffffffu, tag_ok(vga, tag) && tag_ok(vsb, tag) && tag_ok(vcb, tag) && tag_ok(vgb, tag)));
        const float c0 = rbf(1.f + bf_hi(vcb.x)), c1 = rbf(1.f + bf_hi(vcb.y)), c2 = rbf(1.f + bf_hi(vcb.z)), c3 = rbf(1.f + bf_hi(vcb.w));
        const float a0 = c0 * bf_lo(wr.x), a1 = c1 * bf_hi(wr.x), a2 = c2 * bf_lo(wr.y), a3 = c3 * bf_hi(wr.y);
        const uint32_t h0 = pack_bf(a0, a1), h1 = pack_bf(a2, a3);
        const uint32_t t1 = par + PAR_T1 + (lane >> 2) * 64 + (lane & 1) * 32 + (lane & 2) * 2;
        sts1(t1, h0); sts1(t1 + 8, pack_bf(a0 - bf_lo(h0), a1 - bf_hi(h0)));
        sts1(t1 + 16, h1); sts1(t1 + 24, pack_bf(a2 - bf_lo(h1), a3 - bf_hi(h1)));
        sts4(par + PAR_T2 + lane * 32, make_uint4(pack_bf(c0, c1), __byte_perm(vsb.x, vsb.y, 0x7632), __byte_perm(vgb.x, vgb.y, 0x7632), __byte_perm(vga.x, vga.y, 0x7632)));
        sts4(par + PAR_T2 + lane * 32 + 16, make_uint4(pack_bf(c2, c3), __byte_perm(vsb.z, vsb.w, 0x7632), __byte_perm(vgb.z, vgb.w, 0x7632), __byte_perm(vga.z, vga.w, 0x7632)));
      } else {
        const uint4 g = poll4((lane & 2) ? g_mod + 8 - (lane & 1) * 4 : g_mod + 5 * DM + b * 8 + (lane & 1) * 4, tag);
        sts1(par + PAR_CONST + 60, 0);
        if (lane < 2) sts4(par + PAR_CONST + 16 + lane * 16, g);
        else if (lane < 4) sts2(par + PAR_CONST + (lane - 2) * 8, __float_as_uint(untag_sum(g.x, g.y) + untag_sum(g.z, g.w)), epoch);
      }
      __syncwarp();
#pragma unroll 4
      for (int q = XR; q < XE; q++) st_b128(g_xch + ((size_t)b * 8 * 256 + q * 64 + t2) * 4, (epoch & 1) << 16, 0, 0, 0);
      for (int q = 0; q < 2; q++) st_relaxed4(g_stats + ((size_t)cj * SEQ + rb * 128 + q * 64 + t2) * 4, 0, 0, 0, 0);
      if (b < NFFN)
        for (int q = 0; q < 4; q++) st_relaxed4(g_ypart + ((size_t)(q * 32 + (t2 >> 1)) * NFFN + b) * 8 + (t2 & 1) * 4, 0, 0, 0, 0);
      st_relaxed4(g_row + rb * 2 * DM + (t2 >> 5) * DM + cj * 128 + (t2 & 31) * 4, 0, 0, 0, 0);
      __threadfence();
      mbar_arrive(bar_par);
      mbar_wait(bar_gate, 0);
      uint32_t have = 0, n = 0;
      while (true) {
        const uint32_t st = lds1(par + PAR_CONST + 60) >> 7;
        if ((st & 31) != have) {
          const uint32_t* hsrc = g_row + (st & 15) * 2 * DM + t2 * 4;
          uint4 hv[4];
          bool ok = true;
#pragma unroll
          for (int i = 0; i < 4; i++) hv[i] = ld_pairs(hsrc + i * 256);
#pragma unroll
          for (int i = 0; i < 4; i++) {
            sts2(base + ((FT_G >> i * 4) & 15) * UNIT + (warp & 1) * 8192 + 256 + lane * 8, hv[i].x, hv[i].z);
            ok = ok && hv[i].y == tag && hv[i].w == tag;
          }
          have = __all_sync(0xffffffffu, ok) ? st & 31 : 0;
        }
        if ((st ^ have) == 32) break;
        watchdog(n);
      }
      mbar_arrive(bar_sel);
    }
    __syncwarp();
    cluster_arrive();
    {
      const uint32_t tag = epoch % 3 + 1, t3 = tid - 256;
      mbar_wait(bar_win, 0);
      uint2 win = lds2(par + PAR_CONST + 56);
      win.y &= 0x7ff;
      const uint32_t* fsrc = g_row + (win.y >> 7) * 2 * DM + (b >> 1) * 16 + (t3 & 3) * 4 + (b & 1) * 2;
      const uint32_t* ysrc = g_ypart + (size_t)b * NFFN * 8 + min(t3, NFFN - 1) * 4;
      uint2 fh = ld_pair(fsrc), fx = ld_pair(fsrc + DM);
      if (PSL) __nanosleep(PSL);
      uint4 ya = ld_relaxed4(ysrc), yb = ld_relaxed4(ysrc + NFFN * 4);
      const float rwin = __uint_as_float(((int)win.x < 0 ? win.x & 0x7fffffffu : ~win.x) & ~0x1ffu);
      const float rs = rbf(rcp(1.f + __expf(-rbf(rwin))));
      uint32_t n = 0;
      while (__any_sync(0xffffffffu, fh.y != tag || fx.y != tag)) { fh = ld_pair(fsrc); fx = ld_pair(fsrc + DM); watchdog(n); }
      while (!__all_sync(0xffffffffu, tag_ok(ya, tag) && tag_ok(yb, tag))) {
        if (!tag_ok(ya, tag)) ya = ld_relaxed4(ysrc);
        if (!tag_ok(yb, tag)) yb = ld_relaxed4(ysrc + NFFN * 4);
        watchdog(n);
      }
      __syncwarp();
      PROF(8, t3 == 0, 5);
      float y0 = untag_sum(ya.x, yb.x), y1 = untag_sum(ya.y, yb.y), y2 = untag_sum(ya.z, yb.z), y3 = untag_sum(ya.w, yb.w);
      const bool u1 = lane & 2, u2 = lane & 4;
      y0 = (u1 ? y2 : y0) + __shfl_xor_sync(0xffffffffu, u1 ? y0 : y2, 2);
      y1 = (u1 ? y3 : y1) + __shfl_xor_sync(0xffffffffu, u1 ? y1 : y3, 2);
      y0 = (u2 ? y1 : y0) + __shfl_xor_sync(0xffffffffu, u2 ? y0 : y1, 4);
      y0 += __shfl_xor_sync(0xffffffffu, y0, 8);
      if (!(lane & 8)) sts1(par + PAR_RED + 64 + (t3 >> 4) * 32 + ((lane & 1) * 4 + (lane & 2) + ((lane >> 2) & 1)) * 4, __float_as_uint(y0));
      bar_sync(4, 128);
      if (t3 < 4) {
        y0 = 0.f; y1 = 0.f;
#pragma unroll
        for (int w4 = 0; w4 < 7; w4++) {
          const uint2 v = lds2(par + PAR_RED + 64 + w4 * 32 + t3 * 8);
          y0 += __uint_as_float(v.x); y1 += __uint_as_float(v.y);
        }
        const uint2 gv = lds2(par + PAR_CONST + 16 + t3 * 8);
        const uint32_t upd = hmul2(pack_bf(y0, y1), pack_bf(rs, rs));
        *reinterpret_cast<uint32_t*>(P.out + (size_t)win.y * DM + b * 8 + t3 * 2) =
            hadd2(fx.x, hmul2(__byte_perm(gv.x, gv.y, 0x7632), hadd2(fh.x, upd)));
        if (b == 0 && t3 == 0) st_relaxed(&g_epoch, epoch + 1);
      }
      PROF(31, t3 == 0, 36);
    }
    cluster_wait();
  } else {
    const int wg = warp >> 2;

    uint32_t tag;
    {
      uint32_t* const pmod = g_modp + rank * 2 * DM + (b >> 1) * 32 + lane;
      uint32_t* const pln = g_ln1 + (rb * 128 + cj * 16 + warp) * 4;
      const uint32_t cv = ldg_nc1(P.c + rank * 512 + tid * 2);
      const uint32_t epoch = ld_relaxed(&g_epoch);
      if (warp == 0) st_relaxed(pmod, 0);
      if (lane == 0) { st_b128(pln, 0, 0, 0, 0); st_b128(pln + 32, 0, 0, 0, 0); }
      asm volatile("setmaxnreg.inc.sync.aligned.u32 232;");
      sts1(par + tid * 4, pack_bf(silu_f(bf_lo(cv)), silu_f(bf_hi(cv))));
      bar_sync(1, 320);
      tag = epoch % 3 + 1;
#pragma unroll
      for (int part = 0; part < 3; part++) {
        if (part != 1) {
          const uint32_t xa = base + (2 + part / 2) * GST_BYTES + warp * 2048 + lane * 16;
          mbar_wait(bar_hx + part * 4, 0);
          float s0 = 0.f, s1 = 0.f, q0 = 0.f, q1 = 0.f;
#pragma unroll
          for (int q = 0; q < 4; q++) {
            const uint4 xv = lds4(xa + q * 512);
            const uint32_t u[4] = {xv.x, xv.y, xv.z, xv.w};
#pragma unroll
            for (int e = 0; e < 4; e++) { const float lo = bf_lo(u[e]), hi = bf_hi(u[e]); s0 += lo; s1 += hi; q0 += lo * lo; q1 += hi * hi; }
          }
          s0 += s1; q0 += q1;
#pragma unroll
          for (int o = 16; o > 0; o >>= 1) { s0 += __shfl_xor_sync(0xffffffffu, s0, o); q0 += __shfl_xor_sync(0xffffffffu, q0, o); }
          const float mean = s0 * (1.f / DM);
          float mb, sd;
          ln_scalars(mean, fmaxf(q0 * (1.f / DM) - mean * mean, 0.f), mb, sd);
          uint32_t ih, il;
          split_inv(sd, ih, il);
          if (lane == 0) st_b128(pln + part * 16, pack_bf(mb, mb), ih, il, tag);
          PROF(1, tid == 0 && part == 2, 4);
        } else {
          float acc[8];
#pragma unroll
          for (int e = 0; e < 8; e++) acc[e] = 0.f;
          const uint32_t wa = stage + (tid >> 2) * 64 + (((tid ^ (tid >> 3)) & 3) << 4), sa = par + (tid >> 3) * 4, sh = (tid & 4) ? 0x3244 : 0x1044;
          mbar_wait(bar_hw, 0);
#pragma unroll
          for (int p = 0; p < 8; p++) {
            const uint4 w = lds4(wa + p * 4096);
            const float s = __uint_as_float(__byte_perm(lds1(sa + p * 128), 0, sh));
            acc[0] += s * bf_lo(w.x); acc[1] += s * bf_hi(w.x); acc[2] += s * bf_lo(w.y); acc[3] += s * bf_hi(w.y);
            acc[4] += s * bf_lo(w.z); acc[5] += s * bf_hi(w.z); acc[6] += s * bf_lo(w.w); acc[7] += s * bf_hi(w.w);
          }
#pragma unroll
          for (int e = 0; e < 4; e++) {
            const bool up = lane & 16;
            acc[e] = (up ? acc[e + 4] : acc[e]) + __shfl_xor_sync(0xffffffffu, up ? acc[e] : acc[e + 4], 16);
          }
#pragma unroll
          for (int e = 0; e < 2; e++) {
            const bool up = lane & 8;
            acc[e] = (up ? acc[e + 2] : acc[e]) + __shfl_xor_sync(0xffffffffu, up ? acc[e] : acc[e + 2], 8);
          }
          {
            const bool up = lane & 4;
            acc[0] = (up ? acc[1] : acc[0]) + __shfl_xor_sync(0xffffffffu, up ? acc[0] : acc[1], 4);
          }
          sts1(base + 2 * GST_BYTES + warp * 2048 + ((lane & 3) * 8 + (lane >> 2)) * 4, __float_as_uint(acc[0]));
          bar_sync(1, 256);
          if (warp == 0) {
            float s = 0.f;
#pragma unroll
            for (int w8 = 0; w8 < 8; w8++) s += __uint_as_float(lds1(base + 2 * GST_BYTES + w8 * 2048 + lane * 4));
            st_relaxed(pmod, (__float_as_uint(s) & ~3u) | tag);
          }
          PROF(1, tid == 0, 3);
        }
      }
      cluster_wait();
      if (wg == 1) bar_arrive(2, 256);
    }

    float f0 = 0.f, f1 = 0.f;
    const uint32_t rempty = lane < 2 ? mapa(bempty, lane & 1) : 0;
    constexpr uint32_t GE = NSLOT * 8 + 32;
    float o[64], s[64];
#pragma unroll 1
    for (int ps = 0; ps < 3; ps++) {
      {
        const uint32_t xt = ps == 1 ? XT1 : XT2, wt = ps == 1 ? WT1 : WT2;
        const int nst = ps == 2 ? 28 : 14;
        if (ps == 0) {
          float ga[64], gb[64];
#pragma unroll
          for (int i = 0; i < 64; i++) { ga[i] = 0.f; gb[i] = 0.f; }
          uint32_t a[2][16];
          const uint32_t l = fresh_lane();
          uint32_t fa[4];
#pragma unroll
          for (int kk = 0; kk < 4; kk++) fa[kk] = (base + wg * 8192 + frag_offset(warp)) ^ (kk * 32);
          const uint32_t mt = par + (l & 3) * 16;
          auto fetch = [&](int i, uint32_t (&f)[16], uint32_t z) {
            mbar_wait(xfull + (i & 3) * 8, i >> 2);
#pragma unroll
            for (int kk = 0; kk < 4; kk++) ldmatrix4(fa[kk] + (i & 3) * GST_BYTES + z, f[4 * kk], f[4 * kk + 1], f[4 * kk + 2], f[4 * kk + 3]);
          };
          uint4 r0, r1;
          {
            const uint32_t t7 = (warp & 3) * 32 + l;
            const uint32_t* pm = g_modp + wg * DM + ((cj * 128 + t7 * 4) & (DM - 1));
            const uint32_t* pr = g_ln1 + (rb * 128 + warp * 16 + (l >> 2)) * 4;
            uint4 m0 = ld_relaxed4(pm), m1 = ld_relaxed4(pm + 2 * DM);
            r0 = ld_b128(pr); r1 = ld_b128(pr + 32);
            fetch(0, a[0], 0); fetch(1, a[1], 0);
            uint32_t n = 0;
            bool written = false;
#pragma unroll 1
            while (true) {
              uint32_t miss;
              asm volatile("{ .reg .pred p0, p1, p2, p3; .reg .b32 t, u;\n"
                           "lop3.b32 t, %1, %2, %19, 0x7e; lop3.b32 u, %3, %4, %19, 0x7e; or.b32 t, t, u; and.b32 t, t, 3; setp.ne.u32 p0, t, 0;\n"
                           "lop3.b32 t, %5, %6, %19, 0x7e; lop3.b32 u, %7, %8, %19, 0x7e; or.b32 t, t, u; and.b32 t, t, 3; setp.ne.u32 p1, t, 0;\n"
                           "setp.ne.u32 p2, %12, %19; setp.ne.u32 p3, %16, %19;\n"
                           "@p0 ld.relaxed.gpu.global.v4.u32 {%1, %2, %3, %4}, [%17];\n"
                           "@p1 ld.relaxed.gpu.global.v4.u32 {%5, %6, %7, %8}, [%17 + 8192];\n"
                           "@p2 ld.relaxed.gpu.global.v4.u32 {%9, %10, %11, %12}, [%18];\n"
                           "@p3 ld.relaxed.gpu.global.v4.u32 {%13, %14, %15, %16}, [%18 + 128];\n"
                           "or.pred p0, p0, p1; or.pred p2, p2, p3; vote.sync.any.pred p0, p0, 0xffffffff; vote.sync.any.pred p2, p2, 0xffffffff;\n"
                           "selp.u32 t, 1, 0, p0; selp.u32 u, 2, 0, p2; or.b32 %0, t, u; }"
                           : "=r"(miss), "+r"(m0.x), "+r"(m0.y), "+r"(m0.z), "+r"(m0.w), "+r"(m1.x), "+r"(m1.y), "+r"(m1.z), "+r"(m1.w),
                             "+r"(r0.x), "+r"(r0.y), "+r"(r0.z), "+r"(r0.w), "+r"(r1.x), "+r"(r1.y), "+r"(r1.z), "+r"(r1.w)
                           : "l"(pm), "l"(pr), "r"(tag) : "memory");
              if (!(miss & 1) && !written) {
                written = true;
                float c0 = untag_sum(m0.x, m1.x), c1 = untag_sum(m0.y, m1.y), c2 = untag_sum(m0.z, m1.z), c3 = untag_sum(m0.w, m1.w);
                if (wg) { c0 = 1.f + rbf(c0); c1 = 1.f + rbf(c1); c2 = 1.f + rbf(c2); c3 = 1.f + rbf(c3); }
                const uint32_t d = par + (t7 >> 2) * 64 + (t7 & 1) * 32 + (t7 & 2) * 2 + (wg ? 0 : 8);
                sts1(d, pack_bf(c0, c1));
                sts1(d + 16, pack_bf(c2, c3));
                mbar_arrive(bar_mod);
              }
              if (!miss) break;
              watchdog(n);
            }
          }
          const uint32_t zero = r0.w ^ tag;
          auto normalize = [&](uint32_t (&f)[16]) {
#pragma unroll
            for (int k = 0; k < 16; k += 2) { f[k] = ln_norm(f[k], r0.x, r0.y, r0.z); f[k + 1] = ln_norm(f[k + 1], r1.x, r1.y, r1.z); }
          };
          auto modulate = [&](int i, uint32_t (&f)[16]) {
#pragma unroll
            for (int kk = 0; kk < 4; kk++) {
              const uint4 m = lds4(mt + i * 256 + kk * 64);
              f[4 * kk] = MODUL(f[4 * kk], m.x, m.z); f[4 * kk + 1] = MODUL(f[4 * kk + 1], m.x, m.z);
              f[4 * kk + 2] = MODUL(f[4 * kk + 2], m.y, m.w); f[4 * kk + 3] = MODUL(f[4 * kk + 3], m.y, m.w);
            }
            keep(f);
            mbar_arrive_pred(xempty + (i & 3) * 8, l == 0);
          };
          auto publish = [&](int u, uint32_t (&f)[16]) {
#pragma unroll
            for (int kk = 0; kk < 4; kk++) stmatrix4(fa[kk] + OFF_STAGE + u * UNIT, f[4 * kk], f[4 * kk + 1], f[4 * kk + 2], f[4 * kk + 3]);
            __syncwarp();
            mbar_arrive_pred(bar_hpub + u * 8, l == 0);
          };
          auto multiply = [&](int i, uint32_t (&f)[16]) {
            mbar_wait(gfull + (i & 3) * 8, i >> 2);
            const uint64_t db = make_desc(base + (i & 3) * GST_BYTES + UNIT, 8192, 1024);
            wg_fence();
#pragma unroll
            for (int kk = 0; kk < 4; kk++) mma256_rs(ga, gb, f[4 * kk], f[4 * kk + 1], f[4 * kk + 2], f[4 * kk + 3], db + kk * 128);
            wg_commit();
          };
          auto next = [&](int i, uint32_t (&f)[16]) {
            wg_wait<1>();
            mbar_arrive_cl(rempty, GE + ((i + 2) & 3) * 8);
            uint32_t z = zero;
#pragma unroll
            for (int k = 0; k < 16; k += 2) asm volatile("lop3.b32 %0, %1, %2, %0, 0xA8;" : "+r"(z) : "r"(f[k]), "r"(f[k + 1]));
            fetch(i, f, z);
            normalize(f); modulate(i, f); multiply(i, f);
          };
          normalize(a[0]); normalize(a[1]);
          keep(a[0]); keep(a[1]);
          mbar_wait(bar_mod, 0);
          PROF(1, tid == 0, 2);
          modulate(0, a[0]); multiply(0, a[0]); publish(0, a[0]);
          modulate(1, a[1]); multiply(1, a[1]); publish(1, a[1]);
#pragma unroll 1
          for (int i = 2; i < NRS; i += 2) { next(i, a[0]); next(i + 1, a[1]); }
          wg_wait<1>();
          mbar_arrive_cl(rempty, GE + ((NRS + 2) & 3) * 8);
#pragma unroll 1
          for (int i = NRS; i < 14; i++) {
            mbar_wait(xfull + (i & 3) * 8, (i >> 2) & 1);
            mbar_wait(gfull + (i & 3) * 8, (i >> 2) & 1);
            const uint32_t xa = base + (i & 3) * GST_BYTES;
            const uint64_t da = make_desc(xa + wg * 8192, 16, 1024), db = make_desc(xa + UNIT, 8192, 1024);
            if (i == 13) bar_sync(2 + wg, 256);
            wg_fence();
#pragma unroll
            for (int kk = 0; kk < 4; kk++) mma256_ss(ga, gb, da + kk * 2, db + kk * 128, 1);
            wg_commit();
            if (i == 13) bar_arrive(3 - wg, 256);
            wg_wait<1>();
            uint32_t z = zero;
#pragma unroll
            for (int k = 0; k < 16; k += 2) asm volatile("lop3.b32 %0, %1, %2, %0, 0xA8;" : "+r"(z) : "r"(a[1][k]), "r"(a[1][k + 1]));
            mbar_arrive_cl(rempty, GE + ((i + 3) & 3) * 8 + z);
            mbar_arrive_pred(xempty + ((i + 3) & 3) * 8, l == 0 && i != NRS);
          }
          mbar_wait(xfull + 16, 1);
          wg_wait<0>();
          keep(ga); keep(gb);
#pragma unroll
          for (int i = 0; i < 64; i++) {
            asm volatile("mov.b32 %0, %1;" : "=f"(s[i]) : "f"(ga[i]));
            asm volatile("mov.b32 %0, %1;" : "=f"(o[i]) : "f"(gb[i]));
          }
        } else {
          float ga[64], gb[64];
#pragma unroll
          for (int i = 0; i < 64; i++) {
            asm volatile("mov.b32 %0, %1;" : "=f"(ga[i]) : "f"(s[i]));
            asm volatile("mov.b32 %0, %1;" : "=f"(gb[i]) : "f"(o[i]));
          }
#pragma unroll 1
          for (int i = 0; i < nst; i++) {
            mbar_wait(gfull + (i & 3) * 8, (i >> 2) & 1);
            const uint64_t da = make_desc(base + unit_of(xt, i & 3) + wg * 8192, 16, 1024), db = make_desc(base + unit_of(wt, i & 3), 8192, 1024);
            if (i == nst - 1) bar_sync(2 + wg, 256);
            wg_fence();
#pragma unroll
            for (int kk = 0; kk < 4; kk++) mma256_ss(ga, gb, da + kk * 2, db + kk * 128, kk ? 1 : i);
            wg_commit();
            if (i == nst - 1) bar_arrive(3 - wg, 256);
            wg_wait<1>();
            mbar_arrive_cl(rempty, GE + ((i + 3) & 3) * 8, i != 0);
            PROF(4, tid == 0 && (i & 3) == 0, 40 + (ps - 1) * 4 + i / 4);
          }
          wg_wait<0>();
          keep(ga); keep(gb);
#pragma unroll
          for (int i = 0; i < 64; i++) {
            asm volatile("mov.b32 %0, %1;" : "=f"(s[i]) : "f"(ga[i]));
            asm volatile("mov.b32 %0, %1;" : "=f"(o[i]) : "f"(gb[i]));
          }
        }
        mbar_arrive_cl(rempty, GE + (ps == 2 ? 24 : 8));
        if (ps == 2) break;
      }
      const uint32_t qw = base + wg * 8192, qt = QT >> (16 * ps), at = ps ? AT1 : AT0;
      {
        const uint32_t wt = ps ? WT1 : WT0;
        const uint64_t da0 = make_desc(qw + unit_of(qt, 2), 16, 1024), da1 = make_desc(qw + unit_of(qt, 3), 16, 1024);
        const uint64_t db0 = make_desc(base + unit_of(wt, 2), 8192, 1024), db1 = make_desc(base + unit_of(wt, 3), 8192, 1024);
        mbar_wait(gfull + 16, 1);
        bar_sync(2 + wg, 256);
        wg_fence();
#pragma unroll
        for (int kk = 0; kk < 4; kk++) mma_ss<1>(s, da0 + kk * 2, db0 + kk * 128, 1);
        wg_commit();
        mbar_wait(xfull + 24, 1);
        mbar_wait(gfull + 24, 1);
        wg_fence();
#pragma unroll
        for (int kk = 0; kk < 4; kk++) mma_ss<1>(s, da1 + kk * 2, db1 + kk * 128, 1);
        wg_commit();
        bar_arrive(3 - wg, 256);
        mbar_wait(ps == 0 ? bar_pread : bar_ofree + 8, 0);
        mbar_wait(bfull, 0);
        wg_wait<0>();
        keep(s);
        PROF(2, tid == 0, 8 + ps * 8);
        store_chunk<0>(s, qw + unit_of(qt, 0) + frag_offset(warp));
        store_chunk<1>(s, qw + unit_of(qt, 1) + frag_offset(warp));
        fence_async_smem();
        bar_sync(2 + wg, 256);
        wg_fence();
        issue_qk(s, qw + unit_of(qt, 0), qw + unit_of(qt, 1), base + unit_of(at, 0));
        wg_commit();
#pragma unroll
        for (int kk = 0; kk < 8; kk++) mma_ss<1>(o, (kk < 4 ? da0 : da1) + (kk & 3) * 2, (kk < 4 ? db0 : db1) + UNIT / 16 + (kk & 3) * 128, 1);
        wg_commit();
        bar_arrive(3 - wg, 256);
        wg_wait<1>();
        keep(s);
        mbar_arrive_cl(rempty, 0);
      }
      PROF(4, tid == 0 && ps == 1, 61);
      float l0 = 0.25f, l1 = 0.25f;
      auto step = [&](auto odd_c, const int j, uint32_t (&pw)[32], uint32_t (&pr)[32]) {
        constexpr bool ODD = decltype(odd_c)::value;
        const bool first = !ODD && (j & 2) == 0, last = ODD && j == 7;
        const uint32_t ph = (j >> 1) & 1;
        float i0, i1, a0, a1;
        if (first) { i0 = inv_quad_sum(l0); i1 = inv_quad_sum(l1); l0 = 0.f; l1 = 0.f; }
        bool redo = !ODD && (j | ps) == 0, again = false;
        while (true) {
          if (redo) {
            float m0 = fmaxf(s[0], s[1]), m1 = fmaxf(s[2], s[3]);
#pragma unroll
            for (int i = 1; i < 16; i++) { m0 = fmaxf(m0, fmaxf(s[4 * i], s[4 * i + 1])); m1 = fmaxf(m1, fmaxf(s[4 * i + 2], s[4 * i + 3])); }
            m0 = fmaxf(m0, __shfl_xor_sync(0xffffffffu, m0, 1)); m1 = fmaxf(m1, __shfl_xor_sync(0xffffffffu, m1, 1));
            m0 = fmaxf(m0, __shfl_xor_sync(0xffffffffu, m0, 2)); m1 = fmaxf(m1, __shfl_xor_sync(0xffffffffu, m1, 2));
            m0 *= SCL2; m1 *= SCL2;
            if (!first) {
              m0 = fmaxf(m0, f0); m1 = fmaxf(m1, f1);
              const float c0 = ex2(f0 - m0), c1 = ex2(f1 - m1);
              l0 *= c0; l1 *= c1;
              wg_wait<0>();
              keep(o);
#pragma unroll
              for (int i = 0; i < 16; i++) { o[4 * i] *= c0; o[4 * i + 1] *= c0; o[4 * i + 2] *= c1; o[4 * i + 3] *= c1; }
            }
            f0 = m0; f1 = m1;
          }
          float b0 = 0.f, b1 = 0.f;
          a0 = 0.f; a1 = 0.f;
#pragma unroll
          for (int i = 0; i < 16; i++) {
            const float e0 = ex2(fmaf(s[4 * i], SCL2, -f0)), e1 = ex2(fmaf(s[4 * i + 1], SCL2, -f0));
            const float e2 = ex2(fmaf(s[4 * i + 2], SCL2, -f1)), e3 = ex2(fmaf(s[4 * i + 3], SCL2, -f1));
            a0 += e0; b0 += e1; a1 += e2; b1 += e3;
            pw[2 * i] = pack_bf(e0, e1); pw[2 * i + 1] = pack_bf(e2, e3);
            if (i == VREL) {
#pragma unroll
              for (int k = 0; k < 2 * VREL + 2; k++) asm volatile("" : "+r"(pw[k])::"memory");
              mbar_wait(bar_mod, 0);
              wg_wait<0>();
              mbar_arrive_cl(rempty, ODD ? 16 : (j ? 0 : GE + 16), !again);
              if (!ODD) mbar_arrive_cl(rempty, GE + 24, !again && j == 0);
#pragma unroll
              for (int k = 4 * VREL + 4; k < 64; k++) asm volatile("" : "+f"(s[k])::"memory");
            }
          }
          a0 += b0; a1 += b1;
          if (redo) break;
          redo = __any_sync(0xffffffffu, !(a0 + a1 < 0x1p70f));
          if (first) {
            uint32_t m0 = __ballot_sync(0xffffffffu, a0 > 0x1p-50f), m1 = __ballot_sync(0xffffffffu, a1 > 0x1p-50f);
            m0 |= m0 >> 1; m1 |= m1 >> 1; m0 |= m0 >> 2; m1 |= m1 >> 2;
            redo = redo || (m0 & m1 & 0x11111111u) != 0x11111111u;
          }
          if (!redo) break;
          again = true;
        }
        l0 += a0; l1 += a1;
        keep(pw);
        keep(o);
        const uint32_t qo = qt >> (j ? 0 : 8);
        if (first) store_chunk<0>(o, i0, i1, qw + unit_of(qo, 0) + frag_offset(warp));
        keep(o);
        mbar_wait(bfull + (ODD ? 24 : 8), ph);
        bar_sync(2 + wg, 256);
        if (!last) {
          const uint32_t qn = qt >> (j >= 3 ? 8 : 0);
          wg_fence();
          issue_qk(s, qw + unit_of(qn, 0), qw + unit_of(qn, 1), base + unit_of(at, ODD ? 3 : 1));
          wg_commit();
          mbar_wait(bfull + (ODD ? 0 : 16), ODD ? ph ^ 1 : ph);
        }
        if (first) { store_chunk<1>(o, i0, i1, qw + unit_of(qo, 1) + frag_offset(warp)); keep(o); }
        wg_fence();
        issue_pv(o, pw, base + unit_of(at, ODD ? (last ? 3 : 0) : 2), !first);
        wg_commit();
        bar_arrive(3 - wg, 256);
        wg_wait<1>();
        keep(s);
        mbar_arrive_cl(rempty, ODD ? 24 : 8, !last);
        if (first) { fence_async_smem(); mbar_arrive_pred(bar_ofull + wg * 8, j); }
        PROF(4, tid == 0 && ps == 1, 51 + j);
      };
      uint32_t pa[32], pb[32];
#pragma unroll 1
      for (int j = 0; j < 8; j += 2) {
        step(std::false_type{}, j, pa, pb);
        step(std::true_type{}, j + 1, pb, pa);
      }
      {
        const float i0 = inv_quad_sum(l0), i1 = inv_quad_sum(l1);
        wg_wait<0>();
        keep(o);
        mbar_arrive_cl(rempty, 24);
        store_chunk<0>(o, i0, i1, qw + unit_of(qt, 2) + frag_offset(warp));
        store_chunk<1>(o, i0, i1, qw + unit_of(qt, 3) + frag_offset(warp));
        fence_async_smem();
        mbar_arrive(bar_ofull + 16 + wg * 8);
      }
      PROF(2, tid == 0, 10 + ps * 8);
    }

    const int ln = fresh_lane(), g = ln >> 2, tq = ln & 3, ct = warp * 32 + ln;
    const bool lane0 = ln == 0;
    const int lrow0 = warp * 16 + g;
    const int grow0 = rb * 128 + lrow0;
    const uint32_t res = base + OFF_RES, trow = res + wg * 8192 + frag_offset(warp);
    uint32_t xr[32];
    uint4 sv[4], own;
    uint32_t* sp[4];
#pragma unroll
    for (int k = 0; k < 4; k++) sp[k] = g_stats + ((((tq >> 1) * 4 + k) ^ cj) * SEQ + grow0 + (tq & 1) * 8) * 4;
    {
      const uint64_t da = make_desc(base + wg * 8192, 16, 1024), db = make_desc(base, 8192, 1024);
      constexpr int U = UNIT / 16;
#define HALF_STAGE(acc, xu, wu) _Pragma("unroll") for (int kk = 0; kk < 4; kk++) mma_ss<1>(acc, da + (xu) * U + kk * 2, db + (wu) * U + kk * 128, 1)
      PROF(10, ct == PT, 19); STAMP(0);
      cluster_arrive();
      mbar_wait(gfull, 1);
      mbar_wait(gfull + 8, 1);
      bar_sync(2 + wg, 256);
      wg_fence();
      HALF_STAGE(o, 7, 1);
      HALF_STAGE(o, 8, 3);
      wg_commit();
      STAMP(16);
      mbar_wait(gfull + 16, 1);
      STAMP(17);
      wg_fence();
      HALF_STAGE(o, 6, 11);
      wg_commit();
      bar_arrive(3 - wg, 256);
      mbar_wait(bar_par, 0);
      uint32_t* xo = g_xch + ((size_t)b * 8 * 256 + ct) * 4;
      const uint32_t* xi = g_xch + ((size_t)(b ^ 2) * 8 * 256 + ct) * 4;
      const uint32_t par1 = (~lds1(par + PAR_CONST + 4) & 1) << 16;
      uint32_t ga[16];
      uint4 bw[8];
#define LOAD_PAR _Pragma("unroll") for (int i = 0; i < 8; i++) {                                                               \
        ga[2 * i] = lds1(par + PAR_T2 + i * 128 + tq * 16 + 12); ga[2 * i + 1] = lds1(par + PAR_T2 + i * 128 + 64 + tq * 16 + 12); \
        bw[i] = lds4(par + PAR_T1 + i * 64 + tq * 16);                                                                          \
        if (!(g & 1)) { bw[i].x = 0x3f803f80u; bw[i].y = 0x3f803f80u; }                                                         \
      }
      if (PPOS == 0) LOAD_PAR
      wg_wait<1>();
      mbar_arrive_pred(bar_rel, lane0);
      wg_wait<0>();
      keep(o);
      mbar_arrive_pred(bar_ring, lane0);
      PROF(8, ct == PT, 20); STAMP(1);
#define SEND(i) st_b128(xo + (i) * 1024, (pack_bf(o[8 * (i)], o[8 * (i) + 1]) & ~0x10000u) | par1, pack_bf(o[8 * (i) + 2], o[8 * (i) + 3]), \
                        pack_bf(o[8 * (i) + 4], o[8 * (i) + 5]), pack_bf(o[8 * (i) + 6], o[8 * (i) + 7]))
#pragma unroll
      for (int i = 0; i < NS1; i++) SEND(i);
      PROF(8, ct == PT, 21); STAMP(2);
      bar_sync(2 + wg, 256);
      wg_fence();
      HALF_STAGE(s, 7, 0);
      HALF_STAGE(s, 8, 2);
      HALF_STAGE(s, 6, 10);
      wg_commit();
      bar_arrive(3 - wg, 256);
      STAMP(18);
      mbar_wait(gfull + 24, 1);
#pragma unroll
      for (int i = NS1; i < 8; i++) SEND(i);
      uint4 v[8];
#pragma unroll
      for (int i = 0; i < 4; i++) v[i] = ld_b128(xi + i * 1024);
      if (PPOS == 1) LOAD_PAR
      STAMP(19);
      mbar_wait(bar_xres, 0);
      wg_wait<0>();
      mbar_arrive_pred(bar_ring + 8, lane0);
      bar_sync(2 + wg, 256);
      STAMP(20);
#pragma unroll
      for (int i = 4; i < 8; i++) v[i] = ld_b128(xi + i * 1024);
      mbar_wait(bar_xres, 0);
      wg_fence();
      HALF_STAGE(s, 9, 4);
      wg_commit();
      mbar_wait(bar_rx, 0);
      wg_fence();
      HALF_STAGE(s, 1, 5);
      wg_commit();
      bar_arrive(3 - wg, 256);
      STAMP(21);
      wg_wait<0>();
      keep(s);
      mbar_arrive_pred(bar_ring + 16, lane0);
      PROF(10, ct == PT, 23); STAMP(4);
#pragma unroll
      for (int i = 0; i < 16; i += 2) ldmatrix4((trow ^ ((i & 7) << 4)) + (i >> 3) * 16384, xr[2 * i], xr[2 * i + 1], xr[2 * i + 2], xr[2 * i + 3]);
      if (PPOS == 2) LOAD_PAR
      uint32_t pk[32];
      pack_p(s, pk);
      keep(pk);
      {
        uint32_t n = 0, miss;
        do {
          miss = 0;
#pragma unroll
          for (int i = 0; i < 8; i++) miss |= v[i].x ^ par1;
          miss = __any_sync(0xffffffffu, miss & 0x10000u);
          if (miss) {
#pragma unroll
            for (int i = 0; i < 8; i++)
              asm volatile("{ .reg .pred p; .reg .b32 t; xor.b32 t, %0, %5; and.b32 t, t, 0x10000; setp.ne.u32 p, t, 0;\n"
                           "@p ld.relaxed.gpu.global.v4.u32 {%0, %1, %2, %3}, [%4]; }"
                           : "+r"(v[i].x), "+r"(v[i].y), "+r"(v[i].z), "+r"(v[i].w) : "l"(xi + i * 1024), "r"(par1) : "memory");
          }
          watchdog(n);
        } while (miss);
      }
      PROF(8, ct == PT, 22); STAMP(3);
#pragma unroll
      for (int k = 0; k < 4; k++) sv[k] = ESV ? ld_b128(sp[k]) : make_uint4(0, 0, 0, 0);
      float ds[4] = {0.f, 0.f, 0.f, 0.f}, dl[4] = {0.f, 0.f, 0.f, 0.f}, q0[4] = {0.f, 0.f, 0.f, 0.f}, q1[4] = {0.f, 0.f, 0.f, 0.f};
#pragma unroll
      for (int i = 0; i < 8; i++) {
        const uint32_t u0 = hfma2(ga[2 * i], hadd2(pk[4 * i], v[i].x & ~0x10000u), xr[4 * i]);
        const uint32_t u1 = hfma2(ga[2 * i], hadd2(pk[4 * i + 1], v[i].y), xr[4 * i + 1]);
        const uint32_t u2 = hfma2(ga[2 * i + 1], hadd2(pk[4 * i + 2], v[i].z), xr[4 * i + 2]);
        const uint32_t u3 = hfma2(ga[2 * i + 1], hadd2(pk[4 * i + 3], v[i].w), xr[4 * i + 3]);
        xr[4 * i] = u0; xr[4 * i + 1] = u1; xr[4 * i + 2] = u2; xr[4 * i + 3] = u3;
        mma16816(ds, u0, u1, u2, u3, bw[i].x, bw[i].y);
        mma16816(dl, u0, u1, u2, u3, bw[i].z, bw[i].w);
        mma16816(q0, u0, u1, u2, u3, u0, u2);
        mma16816(q1, u0, u1, u2, u3, u1, u3);
      }
      const float sqa = __shfl_sync(0xffffffffu, (g & 1) ? q0[1] : q0[0], g * 4 + (g >> 1));
      const float sqb = __shfl_sync(0xffffffffu, (g & 1) ? q1[3] : q1[2], g * 4 + (g >> 1));
      own = (tq & 1) ? make_uint4(__float_as_uint(ds[2]), __float_as_uint(sqb), __float_as_uint(ds[3] + dl[3]), tag)
                                 : make_uint4(__float_as_uint(ds[0]), __float_as_uint(sqa), __float_as_uint(ds[1] + dl[1]), tag);
      if (tq < 2) st_b128(sp[0], own.x, own.y, own.z, own.w);
    }
    PROF(8, ct == PT, 29); STAMP(5);
    uint32_t mm, ih, il;
    float rbest;
    uint32_t wf[128];
    const uint32_t frow = (ln & 7) + (ln >> 4) * 8;
    const uint32_t wfo = base + (warp & 1) * 8192 + frow * 64 + ((((ln >> 3) & 1) ^ ((frow >> 1) & 3)) << 4);
#define LOAD_WF(m) _Pragma("unroll") for (int f = 0; f < 16; f++) {                                                   \
      const int r = ((f >> 1) * 4 + (m) * 2 + (f & 1)) * 4;                                                           \
      ldmatrix4t(((wfo + unit_of((m) ? FT_U : FT_G, warp >> 1)) ^ ((f & 1) * 32)) + (f >> 1) * 1024, wf[r], wf[r + 1], wf[r + 2], wf[r + 3]); \
    }
    bool early, wait1;
    {
#pragma unroll
      for (int i = 0; i < 16; i += 2) stmatrix4((trow ^ ((i & 7) << 4)) + (i >> 3) * 16384, xr[2 * i], xr[2 * i + 1], xr[2 * i + 2], xr[2 * i + 3]);
      const uint4 cst = lds4(par + PAR_CONST);
      const float A1 = __uint_as_float(cst.x), A2 = __uint_as_float(cst.z);
      uint32_t n = 0;
      early = false; wait1 = false;
#pragma unroll 1
      while (true) {
        uint32_t miss;
        asm volatile("{ .reg .pred p0, p1, p2, p3; .reg .b64 u, v; .reg .b128 w;\n"
                     "setp.ge.u32 p0, %22, 2; setp.ne.and.u32 p0, %4, %21, p0; setp.ne.u32 p1, %8, %21; setp.ne.u32 p2, %12, %21; setp.ne.u32 p3, %16, %21;\n"
                     "@p0 ld.relaxed.gpu.global.v4.u32 {%1, %2, %3, %4}, [%17];\n"
                     "@p1 ld.relaxed.gpu.global.v4.u32 {%5, %6, %7, %8}, [%18];\n"
                     "@p2 ld.relaxed.gpu.global.v4.u32 {%9, %10, %11, %12}, [%19];\n"
                     "@p3 ld.relaxed.gpu.global.v4.u32 {%13, %14, %15, %16}, [%20];\n"
                     "or.pred p0, p0, p1; or.pred p2, p2, p3; or.pred p0, p0, p2; vote.sync.any.pred p0, p0, 0xffffffff; selp.u32 %0, 1, 0, p0; }"
                     : "=r"(miss), "+r"(sv[0].x), "+r"(sv[0].y), "+r"(sv[0].z), "+r"(sv[0].w), "+r"(sv[1].x), "+r"(sv[1].y), "+r"(sv[1].z), "+r"(sv[1].w),
                       "+r"(sv[2].x), "+r"(sv[2].y), "+r"(sv[2].z), "+r"(sv[2].w), "+r"(sv[3].x), "+r"(sv[3].y), "+r"(sv[3].z), "+r"(sv[3].w)
                     : "l"(sp[0]), "l"(sp[1]), "l"(sp[2]), "l"(sp[3]), "r"(tag), "r"(tq) : "memory");
        if (!miss) break;
        wait1 = true;
        if (!early && (b >= NFFN || __all_sync(0xffffffffu, mbar_test(bar_box + (warp >> 1) * 8, 0)))) {
          early = true;
          LOAD_WF(0);
          __syncwarp();
          mbar_arrive_pred(bar_gate, lane0);
        }
        watchdog(n);
      }
      const uint4 v0 = tq < 2 ? own : sv[0], v1 = sv[1], v2 = sv[2], v3 = sv[3];
      PROF(8, ct == PT, 30); STAMP(6);
      float su = (__uint_as_float(v0.x) + __uint_as_float(v1.x)) + (__uint_as_float(v2.x) + __uint_as_float(v3.x));
      float sq = (__uint_as_float(v0.y) + __uint_as_float(v1.y)) + (__uint_as_float(v2.y) + __uint_as_float(v3.y));
      float dt = (__uint_as_float(v0.z) + __uint_as_float(v1.z)) + (__uint_as_float(v2.z) + __uint_as_float(v3.z));
      su += __shfl_xor_sync(0xffffffffu, su, 2); sq += __shfl_xor_sync(0xffffffffu, sq, 2); dt += __shfl_xor_sync(0xffffffffu, dt, 2);
      const float m = su * (1.f / DM);
      float mb, sd;
      ln_scalars(m, fmaxf(sq * (1.f / DM) - m * m, 0.f), mb, sd);
      const float inv = rcp(sd);
      rbest = (dt - mb * A1) * inv + A2;
      mm = pack_bf(mb, mb);
      ih = pack_bf(inv, inv);
      const float lo = inv - bf_lo(ih);
      il = pack_bf(lo, lo);
    }
    int ibest;
    {
      const uint32_t bits = __float_as_uint(rbest);
      const uint32_t key = (((int)bits < 0 ? ~bits : bits | 0x80000000u) & ~0x1ffu) | ((127 - lrow0 - (tq & 1) * 8) << 2) | tag;
      sts1(par + PAR_RED + warp * 4, __reduce_max_sync(0xffffffffu, key));
      PROF(8, ct == PT, 38); STAMP(7);
      uint32_t waited;
      asm volatile("{ .reg .pred p, q; setp.ne.u32 p, %1, 0; barrier.cta.red.or.pred q, 1, 256, p; selp.u32 %0, 1, 0, q; }" : "=r"(waited) : "r"((uint32_t)(wait1 && (wg || CW0))) : "memory");
      const uint4 ka = lds4(par + PAR_RED), kb = lds4(par + PAR_RED + 16);
      const uint32_t k2 = max(max(max(ka.x, ka.y), max(ka.z, ka.w)), max(max(kb.x, kb.y), max(kb.z, kb.w)));
      if (ct == 0 && ((cj & CWM) == 0 || (CWL && !waited))) st_relaxed(g_cand + rb, k2);
      ibest = 127 - ((k2 >> 2) & 127);
    }
    PROF(8, ct == PT, 39); STAMP(8);
    if ((ibest >> 4) == warp) {
      const int src = (ibest & 7) * 4 + ((ibest >> 3) & 1), ch = g * 2;
      const uint32_t cm = __shfl_sync(0xffffffffu, mm, src), ch_ = __shfl_sync(0xffffffffu, ih, src), cl = __shfl_sync(0xffffffffu, il, src);
      const uint32_t xa = res + (ch >> 3) * 16384 + ibest * 128 + (((ch & 7) ^ (ibest & 7)) << 4) + tq * 4;
      const uint32_t x0 = lds1(xa), x1 = lds1(xa ^ 16);
      const uint2 p0 = lds2(par + PAR_T2 + ch * 64 + tq * 16), p1 = lds2(par + PAR_T2 + ch * 64 + 64 + tq * 16);
      uint32_t* dst = g_row + rb * 2 * DM + cj * 128 + ln * 4;
      st_pairs(dst, ln_mod(x0, cm, ch_, cl, p0.x, p0.y), ln_mod(x1, cm, ch_, cl, p1.x, p1.y), tag);
      st_pairs(dst + DM, x0, x1, tag);
      __syncwarp();
    }
    PROF(8, ct == PT, 37); STAMP(9);
    uint32_t wd[64];
    const uint32_t wda = base + unit_of(FT_D, warp >> 1) + (warp & 1) * 8192 + frow * 128 + ((((ln >> 3) & 1) ^ (ln & 7)) << 4);
#define LOAD_WD(f) ldmatrix4t((wda ^ ((((f) >> 1) & 3) * 32)) + ((f) >> 3) * 4096 + ((f) & 1) * 2048, wd[4 * (f)], wd[4 * (f) + 1], wd[4 * (f) + 2], wd[4 * (f) + 3])
    if (!early) {
      if (b < NFFN) mbar_wait(bar_box + (warp >> 1) * 8, 0);
      LOAD_WF(0);
      __syncwarp();
      mbar_arrive_pred(bar_gate, lane0);
    }
    if (b < NFFN) {
      const uint32_t own = base + unit_of(FT_G, warp >> 1) + (warp & 1) * 8192;
      mbar_wait(bar_box + (4 + (warp >> 1)) * 8, 0);
      LOAD_WF(1);
      uint32_t* const ydst = g_ypart + ((size_t)(warp * 16 + tq * 2) * NFFN + b) * 8 + g;
      PROF(8, ct == PT, 31); STAMP(10);
      mbar_wait(bar_box + (8 + (warp >> 1)) * 8, 0);
#pragma unroll
      for (int f = 0; f < WDE; f++) LOAD_WD(f);
      STAMP(11);
      mbar_wait(bar_sel, 0);
      PROF(8, ct == PT, 33); STAMP(12);
      float d[8][4];
#pragma unroll
      for (int i = 0; i < 4; i++) { d[i][0] = 0.f; d[i][1] = 0.f; d[i][2] = 0.f; d[i][3] = 0.f; }
#pragma unroll
      for (int ks = 0; ks < 8; ks++) {
        const uint2 hb = lds2(own + 256 + ks * 32 + tq * 8);
#pragma unroll
        for (int mt = 0; mt < 4; mt++) {
          const int r = ks * 16 + mt * 4;
          mma16816(d[mt], wf[r], wf[r + 1], wf[r + 2], wf[r + 3], hb.x, hb.y);
        }
      }
      sts2(own + (tq * 8 + g) * 8, __float_as_uint((tq & 2) ? ((tq & 1) ? d[1][2] : d[1][0]) : ((tq & 1) ? d[0][2] : d[0][0])),
           __float_as_uint((tq & 2) ? ((tq & 1) ? d[3][2] : d[3][0]) : ((tq & 1) ? d[2][2] : d[2][0])));
      bar_sync(1, 256);
      uint32_t ab[4];
      {
        float G = 0.f, U = 0.f;
        uint2 pv[8];
#pragma unroll
        for (int w8 = 0; w8 < 8; w8++) pv[w8] = lds2(base + ln * 8 + ((FT_G >> (w8 >> 1) * 4) & 15) * UNIT + (w8 & 1) * 8192);
#pragma unroll
        for (int w8 = 0; w8 < 8; w8 += 2) {
          G += __uint_as_float(pv[w8].x) + __uint_as_float(pv[w8 + 1].x);
          U += __uint_as_float(pv[w8].y) + __uint_as_float(pv[w8 + 1].y);
        }
#pragma unroll
        for (int f = WDE; f < 16; f++) LOAD_WD(f);
        const float act = rbf(silu_f(rbf(G))) * rbf(U);
        const uint32_t pk = pack_bf(act, __shfl_down_sync(0xffffffffu, act, 1));
#pragma unroll
        for (int i = 0; i < 4; i++) ab[i] = __shfl_sync(0xffffffffu, pk, i * 8 + tq * 2);
      }
      PROF(8, ct == PT, 34); STAMP(13);
#pragma unroll
      for (int mt = 0; mt < 8; mt++) {
        d[mt][0] = 0.f; d[mt][1] = 0.f; d[mt][2] = 0.f; d[mt][3] = 0.f;
        mma16816(d[mt], wd[mt * 8], wd[mt * 8 + 1], wd[mt * 8 + 2], wd[mt * 8 + 3], ab[0], ab[1]);
        mma16816(d[mt], wd[mt * 8 + 4], wd[mt * 8 + 5], wd[mt * 8 + 6], wd[mt * 8 + 7], ab[2], ab[3]);
      }
#pragma unroll
      for (int i = 0; i < 4; i++) {
        const int m4 = (i >> 1) * 4, e = (i & 1) * 2;
        const float y = (tq & 2) ? ((tq & 1) ? d[m4 + 3][e] : d[m4 + 2][e]) : ((tq & 1) ? d[m4 + 1][e] : d[m4][e]);
        st_relaxed(ydst + (m4 * 2 + (i & 1)) * NFFN * 8, tagf(y, tag));
      }
      PROF(8, ct == PT, 35); STAMP(14);
    }
    mbar_wait(bar_sel, 0);
    mbar_arrive_pred(bar_win, ct == 0);
    const int iwin = lds1(par + PAR_CONST + 60) & 0x7ff;
    {
      const uint32_t mm0 = __shfl_sync(0xffffffffu, mm, ln & ~1), mm1 = __shfl_sync(0xffffffffu, mm, ln | 1);
      const uint32_t ih0 = __shfl_sync(0xffffffffu, ih, ln & ~1), ih1 = __shfl_sync(0xffffffffu, ih, ln | 1);
      const uint32_t il0 = __shfl_sync(0xffffffffu, il, ln & ~1), il1 = __shfl_sync(0xffffffffu, il, ln | 1);
      const bool mine = (iwin >> 4) == rb * 8 + warp;
#pragma unroll 1
      for (int hf = 0; hf < 2; hf++) {
        uint32_t x[16];
#pragma unroll
        for (int i = 0; i < 8; i += 2) ldmatrix4((trow ^ (i << 4)) + hf * 16384, x[2 * i], x[2 * i + 1], x[2 * i + 2], x[2 * i + 3]);
#pragma unroll
        for (int i = 0; i < 8; i++) {
          const uint4 pv = lds4(par + PAR_T2 + (hf * 8 + i) * 64 + tq * 16);
          x[2 * i] = hadd2(x[2 * i], hmul2(pv.z, ln_mod(x[2 * i], mm0, ih0, il0, pv.x, pv.y)));
          x[2 * i + 1] = hadd2(x[2 * i + 1], hmul2(pv.z, ln_mod(x[2 * i + 1], mm1, ih1, il1, pv.x, pv.y)));
        }
        if (mine) {
          uint32_t* dst = reinterpret_cast<uint32_t*>(P.out + (size_t)grow0 * DM + cj * 128 + hf * 64) + tq;
#pragma unroll
          for (int i = 0; i < 8; i++) {
            if (grow0 != iwin) dst[i * 4] = x[2 * i];
            if (grow0 + 8 != iwin) dst[i * 4 + 4 * DM] = x[2 * i + 1];
          }
        } else {
#pragma unroll
          for (int i = 0; i < 8; i += 2) stmatrix4((trow ^ (i << 4)) + hf * 16384, x[2 * i], x[2 * i + 1], x[2 * i + 2], x[2 * i + 3]);
          fence_async_smem();
          __syncwarp();
          if (elect_one()) {
            tma2d_store(&maps.out, res + hf * 16384 + warp * 2048, cj * 128 + hf * 64, rb * 128 + warp * 16);
            asm volatile("cp.async.bulk.commit_group;" ::: "memory");
          }
        }
      }
      asm volatile("cp.async.bulk.wait_group.read 0;" ::: "memory");
    }
    PROF(8, ct == PT, 11); STAMP(15);
    cluster_wait();
  }
}

typedef CUresult (*EncodeFn)(CUtensorMap*, CUtensorMapDataType, cuuint32_t, void*, const cuuint64_t*, const cuuint64_t*,
                             const cuuint32_t*, const cuuint32_t*, CUtensorMapInterleave, CUtensorMapSwizzle,
                             CUtensorMapL2promotion, CUtensorMapFloatOOBfill);

void map2d(EncodeFn enc, CUtensorMap* m, const void* p, uint64_t rows, uint64_t cols, uint32_t brows) {
  cuuint64_t dims[2] = {cols, rows}, strides[1] = {cols * 2};
  cuuint32_t box[2] = {64, brows}, es[2] = {1, 1};
  enc(m, CU_TENSOR_MAP_DATA_TYPE_BFLOAT16, 2, const_cast<void*>(p), dims, strides, box, es, CU_TENSOR_MAP_INTERLEAVE_NONE,
      CU_TENSOR_MAP_SWIZZLE_128B, CU_TENSOR_MAP_L2_PROMOTION_L2_256B, CU_TENSOR_MAP_FLOAT_OOB_FILL_NONE);
}
void map2d_narrow(EncodeFn enc, CUtensorMap* m, const void* p, uint64_t rows, uint64_t cols, uint32_t brows) {
  cuuint64_t dims[2] = {cols, rows}, strides[1] = {cols * 2};
  cuuint32_t box[2] = {32, brows}, es[2] = {1, 1};
  enc(m, CU_TENSOR_MAP_DATA_TYPE_BFLOAT16, 2, const_cast<void*>(p), dims, strides, box, es, CU_TENSOR_MAP_INTERLEAVE_NONE,
      CU_TENSOR_MAP_SWIZZLE_64B, CU_TENSOR_MAP_L2_PROMOTION_L2_64B, CU_TENSOR_MAP_FLOAT_OOB_FILL_NONE);
}
void map3d(EncodeFn enc, CUtensorMap* m, const void* p, uint64_t rows, uint64_t cols, uint32_t brows, uint32_t nch) {
  cuuint64_t dims[3] = {64, rows, cols / 64}, strides[2] = {cols * 2, 128};
  cuuint32_t box[3] = {64, brows, nch}, es[3] = {1, 1, 1};
  enc(m, CU_TENSOR_MAP_DATA_TYPE_BFLOAT16, 3, const_cast<void*>(p), dims, strides, box, es, CU_TENSOR_MAP_INTERLEAVE_NONE,
      CU_TENSOR_MAP_SWIZZLE_128B, CU_TENSOR_MAP_L2_PROMOTION_L2_256B, CU_TENSOR_MAP_FLOAT_OOB_FILL_NONE);
}

}

extern "C" void kernel_launch(void* const* d_in, const int* in_sizes, int n_in, void* d_out, int out_size) {
  (void)in_sizes; (void)n_in; (void)out_size;
  static EncodeFn enc = nullptr;
  if (!enc) {
    void* fn = nullptr;
    cudaDriverEntryPointQueryResult st;
    cudaGetDriverEntryPoint("cuTensorMapEncodeTiled", &fn, cudaEnableDefault, &st);
    enc = (EncodeFn)fn;
    cudaFuncSetAttribute(fused_kernel, cudaFuncAttributeMaxDynamicSharedMemorySize, SMEM_BYTES);
  }
  Maps maps;
  map2d(enc, &maps.x, d_in[0], SEQ, DM, 128);
  map2d(enc, &maps.out, d_out, SEQ, DM, 16);
  map3d(enc, &maps.wq, d_in[3], DM, NQ, 64, 2);
  map3d(enc, &maps.k, d_in[1], 4 * SK, 128, 128, 1);
  map3d(enc, &maps.v, d_in[2], 4 * SK, 128, 128, 1);
  map3d(enc, &maps.wo, d_in[4], NQ, DM, 64, 2);
  map2d_narrow(enc, &maps.wg, d_in[7], DM, FF, 256);
  map2d_narrow(enc, &maps.wu, d_in[8], DM, FF, 256);
  map3d(enc, &maps.wd, d_in[9], FF, DM, 32, 4);
  map2d_narrow(enc, &maps.wm, d_in[11], DM, NMOD, 256);
  Ptrs p;
  p.x = (const __nv_bfloat16*)d_in[0];
  p.w_r = (const __nv_bfloat16*)d_in[6];
  p.w_gate = (const __nv_bfloat16*)d_in[7];
  p.w_up = (const __nv_bfloat16*)d_in[8];
  p.w_down = (const __nv_bfloat16*)d_in[9];
  p.c = (const __nv_bfloat16*)d_in[10];
  p.w_mod = (const __nv_bfloat16*)d_in[11];
  p.out = (__nv_bfloat16*)d_out;
  fused_kernel<<<NMAIN + NHELP, 384, SMEM_BYTES>>>(maps, p);
}
```

```cpp
#include <cuda_runtime.h>
#include <cuda_bf16.h>
#include <cuda.h>
#include <stdint.h>
#include <type_traits>

#define HD 2
#define HDX 2
#define XF 4
#define XE 32
#define XR 0
#define NRS 8
#define FPACE 3
#define GOST 20
#define WB 3
#define WN 24
#define RES0 17
#define RES1 20
#define HU 32
#define NS1 6
#define PG0 0
#define PSL 0
#define CWM 7
#define WDE 16
#define CWL 1
#define CW0 0
#define ESV 1
#define PPOS 1
#define FB0 0
#define FB2 8
#define OPS 8192
#define OFL 0
#define ODS 8
#define MODUL hfma2
#define LNP 1
#define LNS 0
#define VREL 7
#define E0 3

namespace {

constexpr int SEQ = 2048, DM = 1024, NQ = 4096, SK = 2048, WIN = 512, FF = 3584, NMOD = 6144;
constexpr int NMAIN = 128, NHELP = 4, NFFN = 112;
constexpr int NSLOT = 4, SLOT_BYTES = 32768, UNIT = 16384, GST_BYTES = 3 * UNIT;
constexpr uint32_t XT1 = 0xDCBA, XT2 = 0x9687;
constexpr uint32_t WT0 = 0xA741, WT1 = 0x7420, WT2 = 0x4A20;
constexpr uint32_t AT0 = WT1, AT1 = WT2;
constexpr uint32_t QT = 0xDC9696DC;
constexpr int OFF_STAGE = 12 * UNIT;
constexpr uint32_t FT_G = 0x07B3, FT_U = 0xA628, FT_D = 0x5149;
constexpr int OFF_RES = 12 * UNIT;
constexpr int OFF_PAR = 14 * UNIT;
constexpr int OFF_BAR = OFF_PAR + 2528;
constexpr int SMEM_BYTES = OFF_BAR + 544;
static_assert(SMEM_BYTES <= 232448, "smem");

constexpr int PAR_T1 = 0;
constexpr int PAR_T2 = 512;
constexpr int PAR_CONST = 1536;
constexpr int PAR_RED = 1600;
constexpr int PAR_SINK = 2176;

struct Maps {
  CUtensorMap x, wq, k, v, wo, wg, wu, wd, wm, out;
};
struct Ptrs {
  const __nv_bfloat16 *x, *w_r, *c, *w_mod, *w_gate, *w_up, *w_down;
  __nv_bfloat16* out;
};

__device__ __align__(1024) uint8_t g_act[16 * 80 * UNIT];
__device__ __align__(128) uint32_t g_mod[NMOD];
__device__ __align__(128) uint32_t g_modp[2 * 2 * DM];
__device__ __align__(128) uint32_t g_ln1[SEQ * 4];
__device__ __align__(128) uint32_t g_cnt_h[16 * 32];
__device__ __align__(128) uint32_t g_cnt_o[128 * 32];
__device__ __align__(128) uint32_t g_xch[NMAIN * 8 * 256 * 4];
__device__ __align__(128) uint32_t g_stats[8 * SEQ * 4];
__device__ __align__(128) uint32_t g_cand[32];
__device__ __align__(128) uint32_t g_row[16 * 2 * DM];
__device__ __align__(128) uint32_t g_ypart[NMAIN * NFFN * 8];
__device__ uint32_t g_epoch;

__device__ __forceinline__ uint32_t fresh_lane() { uint32_t l; asm volatile("mov.u32 %0, %%laneid;" : "=r"(l)); return l; }
__device__ __forceinline__ uint32_t frag_offset(int warp) {
  const uint32_t l = fresh_lane();
  return ((warp & 3) * 16 + (l & 15)) * 128 + (((l >> 4) ^ (l & 7)) << 4);
}
__device__ __forceinline__ bool elect_one() {
  uint32_t p;
  asm volatile("{ .reg .pred q; elect.sync _|q, 0xffffffff; selp.u32 %0, 1, 0, q; }" : "=r"(p));
  return p;
}
__device__ __forceinline__ uint32_t smem_u32(const void* p) { return (uint32_t)__cvta_generic_to_shared(p); }
__device__ __forceinline__ void mbar_init(uint32_t bar, uint32_t cnt) {
  asm volatile("mbarrier.init.shared::cta.b64 [%0], %1;" ::"r"(bar), "r"(cnt) : "memory");
}
__device__ __forceinline__ void mbar_expect_tx(uint32_t bar, uint32_t bytes) {
  asm volatile("mbarrier.arrive.expect_tx.shared::cta.b64 _, [%0], %1;" ::"r"(bar), "r"(bytes) : "memory");
}
__device__ __forceinline__ void mbar_arrive(uint32_t bar) {
  asm volatile("mbarrier.arrive.shared::cta.b64 _, [%0];" ::"r"(bar) : "memory");
}
__device__ __forceinline__ void mbar_arrive_pred(uint32_t bar, bool p) {
  asm volatile("{ .reg .pred p; setp.ne.b32 p, %1, 0; @p mbarrier.arrive.shared::cta.b64 _, [%0]; }" ::"r"(bar), "r"((int)p) : "memory");
}
__device__ __forceinline__ void mbar_arrive_cl(uint32_t bar, uint32_t off, bool p = true) {
  asm volatile("{ .reg .pred p, q; .reg .b32 a; setp.ne.b32 q, %2, 0; setp.ne.and.b32 p, %0, 0, q; add.u32 a, %0, %1; @p mbarrier.arrive.shared::cluster.b64 _, [a]; }"
               ::"r"(bar), "r"(off), "r"((int)p) : "memory");
}
__device__ __forceinline__ uint32_t mapa(uint32_t addr, uint32_t cta) {
  uint32_t r; asm("mapa.shared::cluster.u32 %0, %1, %2;" : "=r"(r) : "r"(addr), "r"(cta)); return r;
}
__device__ __forceinline__ void cluster_arrive() { asm volatile("barrier.cluster.arrive.relaxed.aligned;" ::: "memory"); }
__device__ __forceinline__ void cluster_wait() { asm volatile("barrier.cluster.wait.aligned;" ::: "memory"); }
__device__ __forceinline__ void watchdog(uint32_t& n) {
}
__device__ __forceinline__ void mbar_wait(uint32_t bar, uint32_t parity) {
  asm volatile("{\n.reg .pred p;\nWAIT_%=:\nmbarrier.try_wait.parity.shared::cta.b64 p, [%0], %1;\n@!p bra WAIT_%=;\n}" ::"r"(bar), "r"(parity) : "memory");
}
__device__ __forceinline__ bool mbar_test(uint32_t bar, uint32_t parity) {
  uint32_t ok;
  asm volatile("{\n.reg .pred p;\nmbarrier.test_wait.parity.shared::cta.b64 p, [%1], %2;\nselp.u32 %0, 1, 0, p;\n}" : "=r"(ok) : "r"(bar), "r"(parity) : "memory");
  return ok;
}
__device__ __forceinline__ uint64_t l2_stream() {
  uint64_t f; asm("createpolicy.fractional.L2::evict_first.b64 %0, 1.0;" : "=l"(f)); return f;
}
__device__ __forceinline__ void tma2d(uint32_t dst, const CUtensorMap* m, int c0, int c1, uint32_t bar) {
  asm volatile("cp.async.bulk.tensor.2d.shared::cluster.global.mbarrier::complete_tx::bytes.L2::cache_hint [%0], [%1, {%3, %4}], [%2], %5;"
               ::"r"(dst), "l"(m), "r"(bar), "r"(c0), "r"(c1), "l"(l2_stream()) : "memory");
}
__device__ __forceinline__ void bulk_load(uint32_t dst, const void* src, uint32_t bytes, uint32_t bar) {
  asm volatile("cp.async.bulk.shared::cluster.global.mbarrier::complete_tx::bytes [%0], [%1], %2, [%3];" ::"r"(dst), "l"(src), "r"(bytes), "r"(bar) : "memory");
}
__device__ __forceinline__ void bulk_load_stream(uint32_t dst, const void* src, uint32_t bytes, uint32_t bar) {
  asm volatile("cp.async.bulk.shared::cluster.global.mbarrier::complete_tx::bytes.L2::cache_hint [%0], [%1], %2, [%3], %4;"
               ::"r"(dst), "l"(src), "r"(bytes), "r"(bar), "l"(l2_stream()) : "memory");
}
__device__ __forceinline__ void tma2d_store(const CUtensorMap* m, uint32_t src, int c0, int c1) {
  asm volatile("cp.async.bulk.tensor.2d.global.shared::cta.bulk_group [%0, {%2, %3}], [%1];" ::"l"(m), "r"(src), "r"(c0), "r"(c1) : "memory");
}
__device__ __forceinline__ void bulk_store(void* dst, uint32_t src, uint32_t bytes) {
  asm volatile("cp.async.bulk.global.shared::cta.bulk_group [%0], [%1], %2;" ::"l"(dst), "r"(src), "r"(bytes) : "memory");
}
__device__ __forceinline__ uint32_t unit_of(uint32_t table, uint32_t i) { return ((table >> (i * 4)) & 15) * UNIT; }
__device__ __forceinline__ void tma3d(uint32_t dst, const CUtensorMap* m, int c0, int c1, int c2, uint32_t bar) {
  asm volatile("cp.async.bulk.tensor.3d.shared::cluster.global.mbarrier::complete_tx::bytes.L2::cache_hint [%0], [%1, {%3, %4, %5}], [%2], %6;"
               ::"r"(dst), "l"(m), "r"(bar), "r"(c0), "r"(c1), "r"(c2), "l"(l2_stream()) : "memory");
}
template <bool STREAM>
__device__ __forceinline__ void tma3d_mc(uint32_t dst, const CUtensorMap* m, int c0, int c1, int c2, uint32_t bar) {
  if (STREAM)
    asm volatile("cp.async.bulk.tensor.3d.shared::cluster.global.mbarrier::complete_tx::bytes.multicast::cluster.L2::cache_hint [%0], [%1, {%3, %4, %5}], [%2], %6, %7;"
                 ::"r"(dst), "l"(m), "r"(bar), "r"(c0), "r"(c1), "r"(c2), "h"((uint16_t)3), "l"(l2_stream()) : "memory");
  else
    asm volatile("cp.async.bulk.tensor.3d.shared::cluster.global.mbarrier::complete_tx::bytes.multicast::cluster [%0], [%1, {%3, %4, %5}], [%2], %6;"
                 ::"r"(dst), "l"(m), "r"(bar), "r"(c0), "r"(c1), "r"(c2), "h"((uint16_t)3) : "memory");
}
__device__ __forceinline__ void prefetch_map(const CUtensorMap* m) {
  asm volatile("prefetch.tensormap [%0];" ::"l"(m) : "memory");
}
__device__ __forceinline__ void fence_async() { asm volatile("fence.proxy.async.global;" ::: "memory"); }
__device__ __forceinline__ void fence_async_smem() { asm volatile("fence.proxy.async.shared::cta;" ::: "memory"); }
__device__ __forceinline__ void bar_sync(int id, int n) { asm volatile("bar.sync %0, %1;" ::"r"(id), "r"(n) : "memory"); }
__device__ __forceinline__ void bar_arrive(int id, int n) { asm volatile("bar.arrive %0, %1;" ::"r"(id), "r"(n) : "memory"); }
__device__ __forceinline__ void wg_fence() { asm volatile("wgmma.fence.sync.aligned;" ::: "memory"); }
__device__ __forceinline__ void wg_commit() { asm volatile("wgmma.commit_group.sync.aligned;" ::: "memory"); }
template <int N> __device__ __forceinline__ void wg_wait() { asm volatile("wgmma.wait_group.sync.aligned %0;" ::"n"(N) : "memory"); }
__device__ __forceinline__ uint64_t make_desc(uint32_t addr, uint32_t lbo, uint32_t sbo) {
  return (uint64_t)((addr & 0x3FFFF) >> 4) | ((uint64_t)(lbo >> 4) << 16) | ((uint64_t)(sbo >> 4) << 32) | (1ull << 62);
}
__device__ __forceinline__ uint32_t ld_relaxed(const uint32_t* p) {
  uint32_t v; asm volatile("ld.relaxed.gpu.global.u32 %0, [%1];" : "=r"(v) : "l"(p) : "memory"); return v;
}
__device__ __forceinline__ uint32_t ld_acquire(const uint32_t* p) {
  uint32_t v; asm volatile("ld.acquire.gpu.global.u32 %0, [%1];" : "=r"(v) : "l"(p) : "memory"); return v;
}
__device__ __forceinline__ uint4 ld_relaxed4(const uint32_t* p) {
  uint4 v; asm volatile("ld.relaxed.gpu.global.v4.u32 {%0,%1,%2,%3}, [%4];" : "=r"(v.x), "=r"(v.y), "=r"(v.z), "=r"(v.w) : "l"(p) : "memory"); return v;
}
__device__ __forceinline__ uint2 ld_relaxed2(const uint32_t* p) {
  uint2 v; asm volatile("ld.relaxed.gpu.global.v2.u32 {%0,%1}, [%2];" : "=r"(v.x), "=r"(v.y) : "l"(p) : "memory"); return v;
}
__device__ __forceinline__ void st_relaxed(uint32_t* p, uint32_t v) {
  asm volatile("st.relaxed.gpu.global.u32 [%0], %1;" ::"l"(p), "r"(v) : "memory");
}
__device__ __forceinline__ void st_relaxed2(uint32_t* p, uint32_t a, uint32_t b) {
  asm volatile("st.relaxed.gpu.global.v2.u32 [%0], {%1,%2};" ::"l"(p), "r"(a), "r"(b) : "memory");
}
__device__ __forceinline__ void st_relaxed4(uint32_t* p, uint32_t a, uint32_t b, uint32_t c, uint32_t d) {
  asm volatile("st.relaxed.gpu.global.v4.u32 [%0], {%1,%2,%3,%4};" ::"l"(p), "r"(a), "r"(b), "r"(c), "r"(d) : "memory");
}
__device__ __forceinline__ void st_b128(uint32_t* p, uint32_t a, uint32_t b, uint32_t c, uint32_t d) {
  asm volatile("{ .reg .b64 u, v; .reg .b128 w; mov.b64 u, {%1, %2}; mov.b64 v, {%3, %4}; mov.b128 w, {u, v}; st.relaxed.gpu.global.b128 [%0], w; }"
               ::"l"(p), "r"(a), "r"(b), "r"(c), "r"(d) : "memory");
}
__device__ __forceinline__ uint4 ld_b128(const uint32_t* p) {
  uint4 r;
  asm volatile("{ .reg .b64 u, v; .reg .b128 w; ld.relaxed.gpu.global.b128 w, [%4]; mov.b128 {u, v}, w; mov.b64 {%0, %1}, u; mov.b64 {%2, %3}, v; }"
               : "=r"(r.x), "=r"(r.y), "=r"(r.z), "=r"(r.w) : "l"(p) : "memory");
  return r;
}
__device__ __forceinline__ void st_pairs(uint32_t* p, uint32_t a, uint32_t b, uint32_t tag) {
  asm volatile("{ .reg .b64 u, v; mov.b64 u, {%1, %3}; mov.b64 v, {%2, %3}; st.relaxed.gpu.global.v2.b64 [%0], {u, v}; }"
               ::"l"(p), "r"(a), "r"(b), "r"(tag) : "memory");
}
__device__ __forceinline__ uint4 ld_pairs(const uint32_t* p) {
  uint4 v;
  asm volatile("{ .reg .b64 u, v; ld.relaxed.gpu.global.v2.b64 {u, v}, [%4]; mov.b64 {%0, %1}, u; mov.b64 {%2, %3}, v; }"
               : "=r"(v.x), "=r"(v.y), "=r"(v.z), "=r"(v.w) : "l"(p) : "memory");
  return v;
}
__device__ __forceinline__ uint2 ld_pair(const uint32_t* p) {
  uint2 v;
  asm volatile("{ .reg .b64 u; ld.relaxed.gpu.global.b64 u, [%2]; mov.b64 {%0, %1}, u; }" : "=r"(v.x), "=r"(v.y) : "l"(p) : "memory");
  return v;
}
__device__ __forceinline__ void red_release(uint32_t* p, uint32_t v) {
  asm volatile("red.release.gpu.global.add.u32 [%0], %1;" ::"l"(p), "r"(v) : "memory");
}
__device__ __forceinline__ uint32_t ldg_nc1(const void* p) {
  uint32_t v;
  asm volatile("ld.global.nc.u32 %0, [%1];" : "=r"(v) : "l"(p));
  return v;
}
__device__ __forceinline__ uint4 ldg_nc4(const void* p) {
  uint4 v; asm volatile("ld.global.nc.L1::no_allocate.v4.u32 {%0,%1,%2,%3}, [%4];" : "=r"(v.x), "=r"(v.y), "=r"(v.z), "=r"(v.w) : "l"(p)); return v;
}
__device__ __forceinline__ uint4 ldg_stream4(const void* p) {
  uint4 v;
  asm volatile("ld.global.nc.L1::no_allocate.L2::cache_hint.v4.u32 {%0,%1,%2,%3}, [%4], %5;" : "=r"(v.x), "=r"(v.y), "=r"(v.z), "=r"(v.w) : "l"(p), "l"(l2_stream()));
  return v;
}
__device__ __forceinline__ void stg4(void* p, uint4 v) {
  asm volatile("st.global.v4.u32 [%0], {%1,%2,%3,%4};" ::"l"(p), "r"(v.x), "r"(v.y), "r"(v.z), "r"(v.w) : "memory");
}
__device__ __forceinline__ void wait_counter(const uint32_t* p, uint32_t target) {
  uint32_t n = 0;
  while (__any_sync(0xffffffffu, (int)(ld_acquire(p) - target) < 0)) { watchdog(n); }
}
__device__ __forceinline__ uint32_t tagf(float v, uint32_t tag) { return (__float_as_uint(v) & ~3u) | tag; }
__device__ __forceinline__ bool tag_ok(uint4 v, uint32_t tag) { return (((v.x ^ tag) | (v.y ^ tag) | (v.z ^ tag) | (v.w ^ tag)) & 3u) == 0; }
__device__ __forceinline__ float untag_sum(uint32_t a, uint32_t b) { return __uint_as_float(a & ~3u) + __uint_as_float(b & ~3u); }
__device__ __forceinline__ uint4 poll4(const uint32_t* p, uint32_t tag) {
  uint4 v = ld_relaxed4(p);
  uint32_t n = 0;
  while (!__all_sync(0xffffffffu, tag_ok(v, tag))) { v = ld_relaxed4(p); watchdog(n); }
  return v;
}
__device__ __forceinline__ float bf_lo(uint32_t v) { return __uint_as_float(v << 16); }
__device__ __forceinline__ float bf_hi(uint32_t v) { return __uint_as_float(v & 0xffff0000u); }
__device__ __forceinline__ uint32_t pack_bf(float lo, float hi) {
  uint32_t r; asm("cvt.rn.bf16x2.f32 %0, %1, %2;" : "=r"(r) : "f"(hi), "f"(lo)); return r;
}
__device__ __forceinline__ float rbf(float v) { return __uint_as_float(pack_bf(0.f, v) & 0xffff0000u); }
__device__ __forceinline__ uint32_t hmul2(uint32_t a, uint32_t b) {
  uint32_t r; asm("mul.rn.bf16x2 %0, %1, %2;" : "=r"(r) : "r"(a), "r"(b)); return r;
}
__device__ __forceinline__ uint32_t hadd2(uint32_t a, uint32_t b) {
  uint32_t r; asm("add.rn.bf16x2 %0, %1, %2;" : "=r"(r) : "r"(a), "r"(b)); return r;
}
__device__ __forceinline__ uint32_t hsub2(uint32_t a, uint32_t b) {
  uint32_t r; asm("sub.rn.bf16x2 %0, %1, %2;" : "=r"(r) : "r"(a), "r"(b)); return r;
}
__device__ __forceinline__ uint32_t hmax2(uint32_t a, uint32_t b) {
  uint32_t r; asm("max.bf16x2 %0, %1, %2;" : "=r"(r) : "r"(a), "r"(b)); return r;
}
__device__ __forceinline__ float rcp(float x) { float r; asm("rcp.approx.ftz.f32 %0, %1;" : "=f"(r) : "f"(x)); return r; }
__device__ __forceinline__ float ex2(float x) { float r; asm("ex2.approx.ftz.f32 %0, %1;" : "=f"(r) : "f"(x)); return r; }
__device__ __forceinline__ void stmatrix4(uint32_t addr, uint32_t a, uint32_t b, uint32_t c, uint32_t d) {
  asm volatile("stmatrix.sync.aligned.m8n8.x4.shared.b16 [%0], {%1,%2,%3,%4};" ::"r"(addr), "r"(a), "r"(b), "r"(c), "r"(d) : "memory");
}
__device__ __forceinline__ void ldmatrix4(uint32_t addr, uint32_t& a, uint32_t& b, uint32_t& c, uint32_t& d) {
  asm volatile("ldmatrix.sync.aligned.m8n8.x4.shared.b16 {%0,%1,%2,%3}, [%4];" : "=r"(a), "=r"(b), "=r"(c), "=r"(d) : "r"(addr) : "memory");
}
__device__ __forceinline__ void ldmatrix4t(uint32_t addr, uint32_t& a, uint32_t& b, uint32_t& c, uint32_t& d) {
  asm volatile("ldmatrix.sync.aligned.m8n8.x4.trans.shared.b16 {%0,%1,%2,%3}, [%4];" : "=r"(a), "=r"(b), "=r"(c), "=r"(d) : "r"(addr) : "memory");
}
__device__ __forceinline__ void mma16816(float (&d)[4], uint32_t a0, uint32_t a1, uint32_t a2, uint32_t a3, uint32_t b0, uint32_t b1) {
  asm volatile("mma.sync.aligned.m16n8k16.row.col.f32.bf16.bf16.f32 {%0,%1,%2,%3}, {%4,%5,%6,%7}, {%8,%9}, {%0,%1,%2,%3};"
               : "+f"(d[0]), "+f"(d[1]), "+f"(d[2]), "+f"(d[3]) : "r"(a0), "r"(a1), "r"(a2), "r"(a3), "r"(b0), "r"(b1));
}
__device__ __forceinline__ void sts1(uint32_t a, uint32_t v) { asm volatile("st.shared.u32 [%0], %1;" ::"r"(a), "r"(v) : "memory"); }
__device__ __forceinline__ uint4 lds4(uint32_t a) {
  uint4 v; asm volatile("ld.shared.v4.u32 {%0,%1,%2,%3}, [%4];" : "=r"(v.x), "=r"(v.y), "=r"(v.z), "=r"(v.w) : "r"(a) : "memory"); return v;
}
__device__ __forceinline__ uint2 lds2(uint32_t a) {
  uint2 v; asm volatile("ld.shared.v2.u32 {%0,%1}, [%2];" : "=r"(v.x), "=r"(v.y) : "r"(a) : "memory"); return v;
}
__device__ __forceinline__ uint32_t lds1(uint32_t a) {
  uint32_t v; asm volatile("ld.shared.u32 %0, [%1];" : "=r"(v) : "r"(a) : "memory"); return v;
}
__device__ __forceinline__ void sts2(uint32_t a, uint32_t x, uint32_t y) { asm volatile("st.shared.v2.u32 [%0], {%1,%2};" ::"r"(a), "r"(x), "r"(y) : "memory"); }
__device__ __forceinline__ void sts4(uint32_t a, uint4 v) {
  asm volatile("st.shared.v4.u32 [%0], {%1,%2,%3,%4};" ::"r"(a), "r"(v.x), "r"(v.y), "r"(v.z), "r"(v.w) : "memory");
}
__device__ __forceinline__ float silu_f(float v) { return __fdividef(v, 1.f + __expf(-v)); }
__device__ __forceinline__ uint32_t hfma2(uint32_t a, uint32_t b, uint32_t c) {
  uint32_t r; asm("fma.rn.bf16x2 %0, %1, %2, %3;" : "=r"(r) : "r"(a), "r"(b), "r"(c)); return r;
}
__device__ __forceinline__ void split_inv(float sd, uint32_t& ih, uint32_t& il) {
  const float inv = rcp(sd);
  ih = pack_bf(inv, inv);
  const float lo = inv - bf_lo(ih);
  il = pack_bf(lo, lo);
}
__device__ __forceinline__ uint32_t ln_norm(uint32_t x, uint32_t mean2, uint32_t ih, uint32_t il) {
  const uint32_t d = hsub2(x, mean2);
  return hfma2(d, ih, hmul2(d, il));
}
__device__ __forceinline__ uint32_t modul(uint32_t n, uint32_t c1, uint32_t sh) { return hadd2(hmul2(n, c1), sh); }
__device__ __forceinline__ uint32_t ln_mod(uint32_t x, uint32_t mean2, uint32_t ih, uint32_t il, uint32_t c1, uint32_t sh) {
  return modul(ln_norm(x, mean2, ih, il), c1, sh);
}

#define R8(a, i) "+f"(a[i]), "+f"(a[i + 1]), "+f"(a[i + 2]), "+f"(a[i + 3]), "+f"(a[i + 4]), "+f"(a[i + 5]), "+f"(a[i + 6]), "+f"(a[i + 7])
#define D64 "{%0,%1,%2,%3,%4,%5,%6,%7,%8,%9,%10,%11,%12,%13,%14,%15,%16,%17,%18,%19,%20,%21,%22,%23,%24,%25,%26,%27,%28,%29,%30,%31," \
            "%32,%33,%34,%35,%36,%37,%38,%39,%40,%41,%42,%43,%44,%45,%46,%47,%48,%49,%50,%51,%52,%53,%54,%55,%56,%57,%58,%59,%60,%61,%62,%63}"
template <int TB>
__device__ __forceinline__ void mma_ss(float (&d)[64], uint64_t da, uint64_t db, int sc) {
  asm volatile("{\n.reg .pred p;\nsetp.ne.b32 p, %66, 0;\n"
               "wgmma.mma_async.sync.aligned.m64n128k16.f32.bf16.bf16 " D64 ", %64, %65, p, 1, 1, 0, %67;\n}"
               : R8(d, 0), R8(d, 8), R8(d, 16), R8(d, 24), R8(d, 32), R8(d, 40), R8(d, 48), R8(d, 56)
               : "l"(da), "l"(db), "r"(sc), "n"(TB));
}
template <int TB>
__device__ __forceinline__ void mma_rs(float (&d)[64], uint32_t a0, uint32_t a1, uint32_t a2, uint32_t a3, uint64_t db, int sc) {
  asm volatile("{\n.reg .pred p;\nsetp.ne.b32 p, %69, 0;\n"
               "wgmma.mma_async.sync.aligned.m64n128k16.f32.bf16.bf16 " D64 ", {%64,%65,%66,%67}, %68, p, 1, 1, %70;\n}"
               : R8(d, 0), R8(d, 8), R8(d, 16), R8(d, 24), R8(d, 32), R8(d, 40), R8(d, 48), R8(d, 56)
               : "r"(a0), "r"(a1), "r"(a2), "r"(a3), "l"(db), "r"(sc), "n"(TB));
}
#define D128 "{%0,%1,%2,%3,%4,%5,%6,%7,%8,%9,%10,%11,%12,%13,%14,%15,%16,%17,%18,%19,%20,%21,%22,%23,%24,%25,%26,%27,%28,%29,%30,%31," \
             "%32,%33,%34,%35,%36,%37,%38,%39,%40,%41,%42,%43,%44,%45,%46,%47,%48,%49,%50,%51,%52,%53,%54,%55,%56,%57,%58,%59,%60,%61,%62,%63," \
             "%64,%65,%66,%67,%68,%69,%70,%71,%72,%73,%74,%75,%76,%77,%78,%79,%80,%81,%82,%83,%84,%85,%86,%87,%88,%89,%90,%91,%92,%93,%94,%95," \
             "%96,%97,%98,%99,%100,%101,%102,%103,%104,%105,%106,%107,%108,%109,%110,%111,%112,%113,%114,%115,%116,%117,%118,%119,%120,%121,%122,%123,%124,%125,%126,%127}"
#define R128(d, e) R8(d, 0), R8(d, 8), R8(d, 16), R8(d, 24), R8(d, 32), R8(d, 40), R8(d, 48), R8(d, 56), \
                   R8(e, 0), R8(e, 8), R8(e, 16), R8(e, 24), R8(e, 32), R8(e, 40), R8(e, 48), R8(e, 56)
__device__ __forceinline__ void mma256_ss(float (&d)[64], float (&e)[64], uint64_t da, uint64_t db, int sc) {
  asm volatile("{\n.reg .pred p;\nsetp.ne.b32 p, %130, 0;\n"
               "wgmma.mma_async.sync.aligned.m64n256k16.f32.bf16.bf16 " D128 ", %128, %129, p, 1, 1, 0, 1;\n}"
               : R128(d, e) : "l"(da), "l"(db), "r"(sc));
}
__device__ __forceinline__ void mma256_rs(float (&d)[64], float (&e)[64], uint32_t a0, uint32_t a1, uint32_t a2, uint32_t a3, uint64_t db) {
  asm volatile("{\n.reg .pred p;\nsetp.ne.b32 p, 1, 0;\n"
               "wgmma.mma_async.sync.aligned.m64n256k16.f32.bf16.bf16 " D128 ", {%128,%129,%130,%131}, %132, p, 1, 1, 1;\n}"
               : R128(d, e) : "r"(a0), "r"(a1), "r"(a2), "r"(a3), "l"(db));
}
template <int N> __device__ __forceinline__ void keep(float (&a)[N]) {
#pragma unroll
  for (int i = 0; i < N; i++) asm volatile("" : "+f"(a[i])::"memory");
}
template <int N> __device__ __forceinline__ void keep(uint32_t (&a)[N]) {
#pragma unroll
  for (int i = 0; i < N; i++) asm volatile("" : "+r"(a[i])::"memory");
}

#define STAMP(idx) do {} while (0)
#define PROF(grp, cond, idx) do {} while (0)

constexpr float SCL2 = 1.4426950408889634f * 0.08838834764831845f;

__device__ __forceinline__ void pack_p(const float (&s)[64], uint32_t (&p)[32]) {
#pragma unroll
  for (int i = 0; i < 32; i++) p[i] = pack_bf(s[2 * i], s[2 * i + 1]);
}

__device__ __forceinline__ void issue_qk(float (&s)[64], uint32_t q0, uint32_t q1, uint32_t kslot) {
  const uint64_t db = make_desc(kslot, 16, 1024), da0 = make_desc(q0, 16, 1024), da1 = make_desc(q1, 16, 1024);
#pragma unroll
  for (int kk = 0; kk < 8; kk++) mma_ss<0>(s, (kk < 4 ? da0 : da1) + (kk & 3) * 2, db + (kk >> 2) * 1024 + (kk & 3) * 2, kk != 0);
}
__device__ __forceinline__ void issue_pv(float (&o)[64], uint32_t (&p)[32], uint32_t vslot, int acc) {
  uint64_t db = make_desc(vslot, 16384, 1024);
#pragma unroll
  for (int kk = 0; kk < 8; kk++)
    mma_rs<1>(o, p[4 * kk], p[4 * kk + 1], p[4 * kk + 2], p[4 * kk + 3], db + kk * 128, kk == 0 ? acc : 1);
}

template <int H>
__device__ __forceinline__ void store_chunk(const float (&a)[64], uint32_t addr) {
#pragma unroll
  for (int i = 8 * H; i < 8 * H + 8; i += 2)
    stmatrix4(addr ^ ((i & 7) << 4), pack_bf(a[4 * i], a[4 * i + 1]), pack_bf(a[4 * i + 2], a[4 * i + 3]),
              pack_bf(a[4 * i + 4], a[4 * i + 5]), pack_bf(a[4 * i + 6], a[4 * i + 7]));
}
template <int H>
__device__ __forceinline__ void store_chunk(const float (&a)[64], float i0, float i1, uint32_t addr) {
#pragma unroll
  for (int i = 8 * H; i < 8 * H + 8; i += 2)
    stmatrix4(addr ^ ((i & 7) << 4), pack_bf(a[4 * i] * i0, a[4 * i + 1] * i0), pack_bf(a[4 * i + 2] * i1, a[4 * i + 3] * i1),
              pack_bf(a[4 * i + 4] * i0, a[4 * i + 5] * i0), pack_bf(a[4 * i + 6] * i1, a[4 * i + 7] * i1));
}
__device__ __forceinline__ float inv_quad_sum(float l) {
  l += __shfl_xor_sync(0xffffffffu, l, 1);
  l += __shfl_xor_sync(0xffffffffu, l, 2);
  return rcp(l);
}

__device__ __forceinline__ void ln_scalars(float mean, float var, float& mb, float& sd) {
  mb = rbf(mean);
  float r; asm("sqrt.approx.ftz.f32 %0, %1;" : "=f"(r) : "f"(rbf(rbf(var) + 1e-5f)));
  sd = rbf(r);
}

__global__ void __cluster_dims__(2, 1, 1) __launch_bounds__(384, 1) fused_kernel(const __grid_constant__ Maps maps, const Ptrs P) {
  extern __shared__ __align__(1024) uint8_t smem_raw[];
  const uint32_t base = smem_u32(smem_raw);
  const int tid = threadIdx.x, lane = tid & 31;
  const int warp = __shfl_sync(0xffffffffu, tid >> 5, 0);
  const int b = blockIdx.x;
  PROF(31, tid == 0, 0);

  if (b >= NMAIN) {
    float* sc = reinterpret_cast<float*>(smem_raw);
    float* red = sc + DM;
    for (int k = tid; k < DM; k += 384) sc[k] = rbf(silu_f(__bfloat162float(P.c[k])));
    __syncthreads();
    if (tid < 256) {
      const int col = 2048 + (b - NMAIN) * 1024 + (tid & 127) * 8, r0 = (tid >> 7) * 512;
      float acc[8];
#pragma unroll
      for (int e = 0; e < 8; e++) acc[e] = 0.f;
#pragma unroll 1
      for (int r = r0; r < r0 + 512; r += HU) {
        uint4 w[HU];
#pragma unroll
        for (int u = 0; u < HU; u++) w[u] = ldg_stream4(P.w_mod + (size_t)(r + u) * NMOD + col);
#pragma unroll
        for (int u = 0; u < HU; u++) {
          float s = sc[r + u];
          acc[0] += s * bf_lo(w[u].x); acc[1] += s * bf_hi(w[u].x); acc[2] += s * bf_lo(w[u].y); acc[3] += s * bf_hi(w[u].y);
          acc[4] += s * bf_lo(w[u].z); acc[5] += s * bf_hi(w[u].z); acc[6] += s * bf_lo(w[u].w); acc[7] += s * bf_hi(w[u].w);
        }
      }
      if (tid >= 128) {
#pragma unroll
        for (int e = 0; e < 8; e++) red[(tid & 127) * 8 + e] = acc[e];
      }
      const uint32_t tag = ld_relaxed(&g_epoch) % 3 + 1;
      bar_sync(1, 256);
      if (tid < 128) {
        uint32_t o[8];
#pragma unroll
        for (int e = 0; e < 8; e++) o[e] = __float_as_uint(rbf(acc[e] + red[tid * 8 + e])) | tag;
        st_relaxed4(g_mod + col, o[0], o[1], o[2], o[3]);
        st_relaxed4(g_mod + col + 4, o[4], o[5], o[6], o[7]);
        const uint4 wr = ldg_nc4(P.w_r + tid * 8);
        const uint32_t wv[4] = {wr.x, wr.y, wr.z, wr.w};
        float dsum = 0.f;
#pragma unroll
        for (int e = 0; e < 8; e++) {
          const float m = bf_hi(o[e]);
          dsum += (b == NMAIN + 2 ? rbf(1.f + m) : m) * ((e & 1) ? bf_hi(wv[e >> 1]) : bf_lo(wv[e >> 1]));
        }
#pragma unroll
        for (int k = 16; k > 0; k >>= 1) dsum += __shfl_xor_sync(0xffffffffu, dsum, k);
        if (lane == 0) st_relaxed(g_mod + (b - NMAIN) * 4 + warp, tagf(dsum, tag));
      }
    }
    PROF(2, tid == 0, 1);
    return;
  }

  const int rank = b & 1;
  const int rb = ((b >> 4) << 1) | rank, cj = (b >> 1) & 7;
  const uint32_t bfull = base + OFF_BAR, bempty = bfull + NSLOT * 8;
  const uint32_t gfull = bempty + NSLOT * 8, gempty = gfull + 32;
  const uint32_t bar_ofull = gempty + 32;
  const uint32_t bar_ofree = bar_ofull + 32;
  const uint32_t bar_par = bar_ofree + 32;
  const uint32_t bar_mod = bar_par + 8;
  const uint32_t bar_pread = bar_mod + 8;
  const uint32_t bar_xres = bar_pread + 8;
  const uint32_t bar_ring = bar_xres + 8;
  const uint32_t bar_box = bar_ring + 24;
  const uint32_t bar_go = bar_box + 96;
  const uint32_t bar_go2 = bar_go + 16;
  const uint32_t bar_cnt = bar_go + 24;
  const uint32_t xfull = bar_go + 40, xempty = xfull + 32;
  const uint32_t bar_hw = xempty + 32, bar_hx = bar_hw + 8;
  const uint32_t bar_hpub = bar_hx + 16;
  const uint32_t bar_win = bar_hpub + 16;
  const uint32_t bar_rx = bar_win + 8;
  const uint32_t bar_sel = bar_rx + 8;
  const uint32_t bar_gate = bar_sel + 8;
  const uint32_t bar_rel = bar_gate + 8;
  const uint32_t bar_od = bar_rel + 8;
  const uint32_t bar_res = bar_go + 8;
  const uint32_t stage = base + OFF_STAGE, par = base + OFF_PAR;

  if (warp == 8 && elect_one()) {
    for (int s = 0; s < NSLOT; s++) { mbar_init(bfull + s * 8, 1); mbar_init(bempty + s * 8, 16); }
    for (int s = 0; s < 4; s++) { mbar_init(gfull + s * 8, 1); mbar_init(gempty + s * 8, 16); mbar_init(xfull + s * 8, 1); mbar_init(xempty + s * 8, 8); mbar_init(bar_ofree + s * 8, 1); mbar_init(bar_ofull + s * 8, 128); }
    mbar_init(bar_par, 64); mbar_init(bar_mod, 256); mbar_init(bar_pread, 2); mbar_init(bar_xres, 1);
    mbar_init(bar_ring, 8); mbar_init(bar_ring + 8, 8); mbar_init(bar_ring + 16, 8);
    mbar_init(bar_go, 1); mbar_init(bar_go2, 1); mbar_init(bar_cnt, 1); mbar_init(bar_cnt + 8, 1); mbar_init(bar_hpub, 8); mbar_init(bar_hpub + 8, 8); mbar_init(bar_res, 1); mbar_init(bar_win, 1); mbar_init(bar_rx, 1); mbar_init(bar_sel, 64); mbar_init(bar_gate, 8); mbar_init(bar_rel, 8); mbar_init(bar_od, 1);
    for (int s = 0; s < 12; s++) mbar_init(bar_box + s * 8, 1);
    asm volatile("fence.mbarrier_init.release.cluster;" ::: "memory");
    prefetch_map(&maps.x); prefetch_map(&maps.wq); prefetch_map(&maps.k); prefetch_map(&maps.v);
  }
  if (warp == 9 && elect_one()) {
    mbar_init(bar_hw, 1); mbar_init(bar_hx, 1); mbar_init(bar_hx + 8, 1);
    asm volatile("fence.mbarrier_init.release.cluster;" ::: "memory");
    mbar_expect_tx(bar_hw, 32768);
    mbar_expect_tx(bar_hx, 16384);
    mbar_expect_tx(bar_hx + 8, 16384);
    const __nv_bfloat16* xs = P.x + (size_t)(rb * 128 + cj * 16) * DM;
    bulk_load(base + 2 * GST_BYTES, xs, 16384, bar_hx);
    tma2d(stage, &maps.wm, (b >> 1) * 32, rank * 512, bar_hw);
    tma2d(stage + 16384, &maps.wm, (b >> 1) * 32, rank * 512 + 256, bar_hw);
    bulk_load(base + 3 * GST_BYTES, xs + 8 * DM, 16384, bar_hx + 8);
  }
  cluster_arrive();

  if (warp >= 8) {
    asm volatile("setmaxnreg.dec.sync.aligned.u32 40;");
    if (warp < 10) bar_arrive(1, 320);
    const uint32_t epoch = ld_relaxed(&g_epoch);
    cluster_wait();
    if (warp == 8) {
      const int kvrow = (cj >> 1) * SK + (SK - WIN);
      int wch = cj * 8 + rank * 2;
#pragma unroll 1
      for (int ps = 0; ps < 3; ps++) {
        const CUtensorMap* mw = ps == 2 ? &maps.wo : &maps.wq;
        const uint32_t xt = ps == 1 ? XT1 : XT2, wt = ps == 0 ? WT0 : (ps == 1 ? WT1 : WT2);
        const int nst = ps == 2 ? 32 : 16;
#pragma unroll 1
        for (int i = 0; i < nst; i++) {
          const uint32_t bf = gfull + (i & 3) * 8;
          const int kt = ps == 2 ? (((cj & 1) * 4 + ((i >> 1) & 3)) * 4 + (i >> 3)) * 2 + (i & 1) : (i + (ps ? 0 : b & 14)) & 15;
          const uint32_t wd = base + unit_of(wt, i & 3) + rank * UNIT, xd = base + unit_of(xt, i & 3);
          const uint8_t* xs = g_act + (uint32_t)(rb * 80 + (ps - 1) * 16 + kt) * UNIT;
          if (ps == 0 && i == HD) mbar_wait(bar_mod, 0);
          const bool xfirst = ps && i < 2;
          if (ps == 2 && i == 0) mbar_wait(bar_ofree + 24, 0);
          if (i == 0) fence_async();
          mbar_wait(gempty + (i & 3) * 8, ((i >> 2) & 1) ^ 1);
          if (elect_one()) {
            mbar_expect_tx(bf, ps ? GST_BYTES : 2 * UNIT);
            if (xfirst) bulk_load_stream(xd, xs, UNIT, bf);
          }
          if (ps && i < 4) mbar_wait(bempty + i * 8, 1);
          if (elect_one()) tma3d_mc<true>(wd, mw, 0, (i == 31 ? kt ^ (rank * 32) : kt) * 64, i == 31 ? cj * 2 : wch, bf);
          if (ps) {
            if (i == 16 || i == 24) { mbar_wait(bar_cnt + i - 16, 0); fence_async(); }
            if (i == RES0) mbar_wait(bar_res, 0);
            if (i == 2) mbar_wait(bar_ofree + (ps - 1) * 16, 0);
            if (elect_one()) {
              if (i == 31) bulk_load(xd, xs, UNIT, bf); else if (!xfirst) bulk_load_stream(xd, xs, UNIT, bf);
              mbar_arrive_pred(bar_go, i == GOST - 1);
              mbar_arrive_pred(bar_od, i == ODS);
              if (i == RES0) mbar_expect_tx(bar_xres, 32768);
              if (i == RES0 || i == RES1) tma2d(base + OFF_RES + (i == RES1) * UNIT, &maps.x, cj * 128 + (i == RES1) * 64, rb * 128, bar_xres);
            }
          }
        }
        if (ps == 2) break;
        wch = ps ? ((wch >> 3) ^ rank) * 2 : wch + 4;
#pragma unroll 1
        for (int u = 0; u < 16; u++) {
          const bool isk = (u == 0) || ((u & 1) && u < 15);
          const int blk = (isk ? (u + 1) >> 1 : (u == 15 ? 7 : (u >> 1) - 1)) & 3;
          const uint32_t sl = base + unit_of(ps ? AT1 : AT0, u & 3) + rank * UNIT, bf = bfull + (u & 3) * 8;
          if (u < 4) mbar_wait(gempty + ((u + 1) >> 1) * 8, 1);
          mbar_wait(bempty + (u & 3) * 8, ((u >> 2) & 1) ^ 1);
          if (elect_one()) {
            mbar_arrive_pred(bar_go2, ps && u == PG0);
            mbar_expect_tx(bf, SLOT_BYTES);
            tma3d_mc<false>(sl, isk ? &maps.k : &maps.v, 0, kvrow + blk * 128, rank, bf);
          }
        }
      }
      if (elect_one()) mbar_expect_tx(bar_rx, UNIT);
      mbar_wait(bar_rel, 0);
      if (elect_one()) {
        bulk_load_stream(base + UNIT, g_act + (uint32_t)(rb * 80 + 16 + 63 - (cj & 1) * 32) * UNIT, UNIT, bar_rx);
      }
      if (b < NFFN) {
#pragma unroll 1
        for (int u = 0; u < 12; u++) {
          const uint32_t dst = base + unit_of(u < 4 ? FT_G : (u < 8 ? FT_U : FT_D), u & 3);
          if (elect_one()) mbar_expect_tx(bar_box + u * 8, UNIT);
          if (u == FB0 || u == 2 || u == FB2) mbar_wait(bar_ring + (u == FB2 ? 16 : (u + 6) & 8), 0);
          if (u >= FPACE) mbar_wait(bar_box + (u - FPACE) * 8, 0);
          if (elect_one()) {
            if (u < 8) tma2d(dst, u < 4 ? &maps.wg : &maps.wu, b * 32, (u & 3) * 256, bar_box + u * 8);
            else tma3d(dst, &maps.wd, 0, b * 32, (u - 8) * 4, bar_box + u * 8);
          }
        }
      }
    } else if (warp == 9) {
      const uint32_t target = 8 * (epoch + 1);
      uint32_t hmask = 0;
#pragma unroll 1
      for (int i = 0; i < 16; i++) {
        if (i == HDX) mbar_wait(bar_mod, 0);
        const uint32_t need = i == 15 ? 0xffffu : 1u << ((2 * cj + i) & 15);
        if (i >= NRS && (hmask & need) != need) {
          uint32_t n = 0;
          do { hmask = __ballot_sync(0xffffffffu, ld_acquire(&g_cnt_h[rb * 32 + (lane & 15)]) == epoch + 1); watchdog(n); } while ((hmask & need) != need);
          PROF(1, lane == 0 && i == NRS, 26);
          fence_async();
        }
        mbar_wait(xempty + (i & 3) * 8, ((i >> 2) & 1) ^ 1);
        if (elect_one()) {
          mbar_expect_tx(xfull + (i & 3) * 8, UNIT);
          if (i < NRS) tma2d(base + (i & 3) * GST_BYTES, &maps.x, ((2 * cj + i) & 15) * 64, rb * 128, xfull + (i & 3) * 8);
          else bulk_load_stream(base + (i & 3) * GST_BYTES, g_act + (uint32_t)(rb * 80 + ((2 * cj + i) & 15)) * UNIT, UNIT, xfull + (i & 3) * 8);
        }
      }
      prefetch_map(&maps.wo);
#pragma unroll 1
      for (int t = 0; t < 4; t++) {
        if (t & 1) mbar_wait(bar_od, t >> 1);
#pragma unroll 1
        for (int p = 0; p < 32768 / OPS; p++) {
          const uint32_t w = p / (16384 / OPS), c = (p / (8192 / OPS)) & 1, off = w * 8192 + (p % (8192 / OPS)) * OPS;
          mbar_wait(bar_ofull + (t & 1) * 16 + w * 8, t >> 1);
          if (elect_one()) {
            bulk_store(g_act + (uint32_t)(rb * 80 + 16 + (cj * 4 + t) * 2 + c) * UNIT + off, base + unit_of(QT, 2 * t + c) + off, OPS);
            asm volatile("cp.async.bulk.commit_group;" ::: "memory");
            asm volatile("cp.async.bulk.wait_group.read %0;" ::"n"(OFL) : "memory");
          }
        }
        if (elect_one()) {
          asm volatile("cp.async.bulk.wait_group.read 0;" ::: "memory");
          mbar_arrive(t < 3 ? bar_ofree + t * 8 : bar_res);
          asm volatile("cp.async.bulk.wait_group 0;" ::: "memory");
          fence_async();
          red_release(&g_cnt_o[((rb * 4 + t) * 2 + (cj >> 2)) * 32], 2);
        }
        if (t) {
          wait_counter(&g_cnt_o[(rb * 8 + 2 * t + (cj & 1)) * 32], target);
          if (t & 1) wait_counter(&g_cnt_o[(rb * 8 + (t == 1 ? cj & 1 : 7 - (cj & 1))) * 32], target);
          if (elect_one()) mbar_arrive(t == 1 ? bar_ofree + 24 : bar_cnt + t * 8 - 16);
        }
      }
      PROF(2, lane == 0, 27);
      const uint32_t tag = epoch % 3 + 1;
      const uint32_t* inbox = g_cand + (lane & 15);
      mbar_wait(bar_ring + 16, 0);
      uint32_t c0 = ld_relaxed(inbox), n = 0;
#define CAND_STEP(cv)                                                                                        \
      {                                                                                                      \
        const bool valid = (cv & 3u) == tag, all = __all_sync(0xffffffffu, valid);                           \
        const uint32_t best = __reduce_max_sync(0xffffffffu, valid ? cv : 0u);                               \
        const uint32_t blk = __ffs(__ballot_sync(0xffffffffu, cv == best)) - 1;                              \
        if (best) sts2(par + PAR_CONST + 56, best, (blk << 7 | (~best >> 2 & 127)) | (all ? 0x1800 : 0x800)); \
        if (all) break;                                                                                      \
        cv = ld_relaxed(inbox);                                                                              \
      }
      while (true) { CAND_STEP(c0) watchdog(n); }
    } else {
      const int t2 = tid - 320;
      mbar_wait(bar_hpub + (warp & 1) * 8, 0);
      PROF(1, t2 == 0, 24);
#pragma unroll 1
      for (int c = 0; c < 8; c++) {
        const uint32_t off = (warp & 1) * UNIT + c * 2048 + lane * 16;
        uint8_t* dst = g_act + (uint32_t)(rb * 80 + cj * 2) * UNIT + off;
        const uint4 v0 = lds4(stage + off), v1 = lds4(stage + off + 512), v2 = lds4(stage + off + 1024), v3 = lds4(stage + off + 1536);
        stg4(dst, v0); stg4(dst + 512, v1); stg4(dst + 1024, v2); stg4(dst + 1536, v3);
      }
      __syncwarp();
      PROF(1, t2 == 0, 15);
      if (lane == 0) {
        mbar_arrive(bar_pread);
        red_release(&g_cnt_h[rb * 32 + cj * 2 + (warp & 1)], 1);
        PROF(1, t2 == 0, 25);
        prefetch_map(&maps.wg); prefetch_map(&maps.wu); prefetch_map(&maps.wd); prefetch_map(&maps.out);
      }
      __syncwarp();
      if (b < NFFN) {
        mbar_wait(bar_go2, 0);
        const __nv_bfloat16* pg = ((b & 1) ? P.w_up : P.w_gate) + (b >> 1) * 64 + (size_t)t2 * FF;
        const __nv_bfloat16* pd = P.w_down + (size_t)b * 32768 + t2 * 64;
        PROF(2, t2 == 0, 13);
#pragma unroll 1
        for (int i = 0; i < WN; i += WB) {
          uint32_t v[WB];
#pragma unroll
          for (int u = 0; u < WB; u++) {
            const int k = i + u;
            asm volatile("ld.global.cg.L2::128B.u32 %0, [%1];" : "=r"(v[u]) : "l"(k < 16 ? pg + (size_t)k * 64 * FF : pd + (k - 16) * 4096));
          }
#pragma unroll
          for (int u = 1; u < WB; u++) v[0] ^= v[u];
          sts1(par + PAR_SINK + t2 * 4, v[0]);
        }
        PROF(2, t2 == 0, 14);
      }
      const uint32_t tag = epoch % 3 + 1;
      mbar_wait(bar_go, 0);
      if (warp == 10) {
        const uint32_t* src = g_mod + 2 * DM + cj * 128 + lane * 4;
        const uint2 wr = *reinterpret_cast<const uint2*>(P.w_r + cj * 128 + lane * 4);
        uint4 vga, vsb, vcb, vgb;
        uint32_t n = 0;
        do {
          vga = ld_relaxed4(src); vsb = ld_relaxed4(src + DM); vcb = ld_relaxed4(src + 2 * DM); vgb = ld_relaxed4(src + 3 * DM);
          watchdog(n);
        } while (!__all_sync(0xffffffffu, tag_ok(vga, tag) && tag_ok(vsb, tag) && tag_ok(vcb, tag) && tag_ok(vgb, tag)));
        const float c0 = rbf(1.f + bf_hi(vcb.x)), c1 = rbf(1.f + bf_hi(vcb.y)), c2 = rbf(1.f + bf_hi(vcb.z)), c3 = rbf(1.f + bf_hi(vcb.w));
        const float a0 = c0 * bf_lo(wr.x), a1 = c1 * bf_hi(wr.x), a2 = c2 * bf_lo(wr.y), a3 = c3 * bf_hi(wr.y);
        const uint32_t h0 = pack_bf(a0, a1), h1 = pack_bf(a2, a3);
        const uint32_t t1 = par + PAR_T1 + (lane >> 2) * 64 + (lane & 1) * 32 + (lane & 2) * 2;
        sts1(t1, h0); sts1(t1 + 8, pack_bf(a0 - bf_lo(h0), a1 - bf_hi(h0)));
        sts1(t1 + 16, h1); sts1(t1 + 24, pack_bf(a2 - bf_lo(h1), a3 - bf_hi(h1)));
        sts4(par + PAR_T2 + lane * 32, make_uint4(pack_bf(c0, c1), __byte_perm(vsb.x, vsb.y, 0x7632), __byte_perm(vgb.x, vgb.y, 0x7632), __byte_perm(vga.x, vga.y, 0x7632)));
        sts4(par + PAR_T2 + lane * 32 + 16, make_uint4(pack_bf(c2, c3), __byte_perm(vsb.z, vsb.w, 0x7632), __byte_perm(vgb.z, vgb.w, 0x7632), __byte_perm(vga.z, vga.w, 0x7632)));
      } else {
        const uint4 g = poll4((lane & 2) ? g_mod + 8 - (lane & 1) * 4 : g_mod + 5 * DM + b * 8 + (lane & 1) * 4, tag);
        sts1(par + PAR_CONST + 60, 0);
        if (lane < 2) sts4(par + PAR_CONST + 16 + lane * 16, g);
        else if (lane < 4) sts2(par + PAR_CONST + (lane - 2) * 8, __float_as_uint(untag_sum(g.x, g.y) + untag_sum(g.z, g.w)), epoch);
      }
      __syncwarp();
#pragma unroll 4
      for (int q = XR; q < XE; q++) st_b128(g_xch + ((size_t)b * 8 * 256 + q * 64 + t2) * 4, (epoch & 1) << 16, 0, 0, 0);
      for (int q = 0; q < 2; q++) st_relaxed4(g_stats + ((size_t)cj * SEQ + rb * 128 + q * 64 + t2) * 4, 0, 0, 0, 0);
      if (b < NFFN)
        for (int q = 0; q < 4; q++) st_relaxed4(g_ypart + ((size_t)(q * 32 + (t2 >> 1)) * NFFN + b) * 8 + (t2 & 1) * 4, 0, 0, 0, 0);
      st_relaxed4(g_row + rb * 2 * DM + (t2 >> 5) * DM + cj * 128 + (t2 & 31) * 4, 0, 0, 0, 0);
      __threadfence();
      mbar_arrive(bar_par);
      mbar_wait(bar_gate, 0);
      uint32_t have = 0, n = 0;
      while (true) {
        const uint32_t st = lds1(par + PAR_CONST + 60) >> 7;
        if ((st & 31) != have) {
          const uint32_t* hsrc = g_row + (st & 15) * 2 * DM + t2 * 4;
          uint4 hv[4];
          bool ok = true;
#pragma unroll
          for (int i = 0; i < 4; i++) hv[i] = ld_pairs(hsrc + i * 256);
#pragma unroll
          for (int i = 0; i < 4; i++) {
            sts2(base + ((FT_G >> i * 4) & 15) * UNIT + (warp & 1) * 8192 + 256 + lane * 8, hv[i].x, hv[i].z);
            ok = ok && hv[i].y == tag && hv[i].w == tag;
          }
          have = __all_sync(0xffffffffu, ok) ? st & 31 : 0;
        }
        if ((st ^ have) == 32) break;
        watchdog(n);
      }
      mbar_arrive(bar_sel);
    }
    __syncwarp();
    cluster_arrive();
    {
      const uint32_t tag = epoch % 3 + 1, t3 = tid - 256;
      mbar_wait(bar_win, 0);
      uint2 win = lds2(par + PAR_CONST + 56);
      win.y &= 0x7ff;
      const uint32_t* fsrc = g_row + (win.y >> 7) * 2 * DM + (b >> 1) * 16 + (t3 & 3) * 4 + (b & 1) * 2;
      const uint32_t* ysrc = g_ypart + (size_t)b * NFFN * 8 + min(t3, NFFN - 1) * 4;
      uint2 fh = ld_pair(fsrc), fx = ld_pair(fsrc + DM);
      if (PSL) __nanosleep(PSL);
      uint4 ya = ld_relaxed4(ysrc), yb = ld_relaxed4(ysrc + NFFN * 4);
      const float rwin = __uint_as_float(((int)win.x < 0 ? win.x & 0x7fffffffu : ~win.x) & ~0x1ffu);
      const float rs = rbf(rcp(1.f + __expf(-rbf(rwin))));
      uint32_t n = 0;
      while (__any_sync(0xffffffffu, fh.y != tag || fx.y != tag)) { fh = ld_pair(fsrc); fx = ld_pair(fsrc + DM); watchdog(n); }
      while (!__all_sync(0xffffffffu, tag_ok(ya, tag) && tag_ok(yb, tag))) {
        if (!tag_ok(ya, tag)) ya = ld_relaxed4(ysrc);
        if (!tag_ok(yb, tag)) yb = ld_relaxed4(ysrc + NFFN * 4);
        watchdog(n);
      }
      __syncwarp();
      PROF(8, t3 == 0, 5);
      float y0 = untag_sum(ya.x, yb.x), y1 = untag_sum(ya.y, yb.y), y2 = untag_sum(ya.z, yb.z), y3 = untag_sum(ya.w, yb.w);
      const bool u1 = lane & 2, u2 = lane & 4;
      y0 = (u1 ? y2 : y0) + __shfl_xor_sync(0xffffffffu, u1 ? y0 : y2, 2);
      y1 = (u1 ? y3 : y1) + __shfl_xor_sync(0xffffffffu, u1 ? y1 : y3, 2);
      y0 = (u2 ? y1 : y0) + __shfl_xor_sync(0xffffffffu, u2 ? y0 : y1, 4);
      y0 += __shfl_xor_sync(0xffffffffu, y0, 8);
      if (!(lane & 8)) sts1(par + PAR_RED + 64 + (t3 >> 4) * 32 + ((lane & 1) * 4 + (lane & 2) + ((lane >> 2) & 1)) * 4, __float_as_uint(y0));
      bar_sync(4, 128);
      if (t3 < 4) {
        y0 = 0.f; y1 = 0.f;
#pragma unroll
        for (int w4 = 0; w4 < 7; w4++) {
          const uint2 v = lds2(par + PAR_RED + 64 + w4 * 32 + t3 * 8);
          y0 += __uint_as_float(v.x); y1 += __uint_as_float(v.y);
        }
        const uint2 gv = lds2(par + PAR_CONST + 16 + t3 * 8);
        const uint32_t upd = hmul2(pack_bf(y0, y1), pack_bf(rs, rs));
        *reinterpret_cast<uint32_t*>(P.out + (size_t)win.y * DM + b * 8 + t3 * 2) =
            hadd2(fx.x, hmul2(__byte_perm(gv.x, gv.y, 0x7632), hadd2(fh.x, upd)));
        if (b == 0 && t3 == 0) st_relaxed(&g_epoch, epoch + 1);
      }
      PROF(31, t3 == 0, 36);
    }
    cluster_wait();
  } else {
    const int wg = warp >> 2;

    uint32_t tag;
    {
      uint32_t* const pmod = g_modp + rank * 2 * DM + (b >> 1) * 32 + lane;
      uint32_t* const pln = g_ln1 + (rb * 128 + cj * 16 + warp) * 4;
      const uint32_t cv = ldg_nc1(P.c + rank * 512 + tid * 2);
      const uint32_t epoch = ld_relaxed(&g_epoch);
      if (warp == 0) st_relaxed(pmod, 0);
      if (lane == 0) { st_b128(pln, 0, 0, 0, 0); st_b128(pln + 32, 0, 0, 0, 0); }
      asm volatile("setmaxnreg.inc.sync.aligned.u32 232;");
      sts1(par + tid * 4, pack_bf(silu_f(bf_lo(cv)), silu_f(bf_hi(cv))));
      bar_sync(1, 320);
      tag = epoch % 3 + 1;
#pragma unroll
      for (int part = 0; part < 3; part++) {
        if (part != 1) {
          const uint32_t xa = base + (2 + part / 2) * GST_BYTES + warp * 2048 + lane * 16;
          mbar_wait(bar_hx + part * 4, 0);
          float s0 = 0.f, s1 = 0.f, q0 = 0.f, q1 = 0.f;
#pragma unroll
          for (int q = 0; q < 4; q++) {
            const uint4 xv = lds4(xa + q * 512);
            const uint32_t u[4] = {xv.x, xv.y, xv.z, xv.w};
#pragma unroll
            for (int e = 0; e < 4; e++) { const float lo = bf_lo(u[e]), hi = bf_hi(u[e]); s0 += lo; s1 += hi; q0 += lo * lo; q1 += hi * hi; }
          }
          s0 += s1; q0 += q1;
#pragma unroll
          for (int o = 16; o > 0; o >>= 1) { s0 += __shfl_xor_sync(0xffffffffu, s0, o); q0 += __shfl_xor_sync(0xffffffffu, q0, o); }
          const float mean = s0 * (1.f / DM);
          float mb, sd;
          ln_scalars(mean, fmaxf(q0 * (1.f / DM) - mean * mean, 0.f), mb, sd);
          uint32_t ih, il;
          split_inv(sd, ih, il);
          if (lane == 0) st_b128(pln + part * 16, pack_bf(mb, mb), ih, il, tag);
          PROF(1, tid == 0 && part == 2, 4);
        } else {
          float acc[8];
#pragma unroll
          for (int e = 0; e < 8; e++) acc[e] = 0.f;
          const uint32_t wa = stage + (tid >> 2) * 64 + (((tid ^ (tid >> 3)) & 3) << 4), sa = par + (tid >> 3) * 4, sh = (tid & 4) ? 0x3244 : 0x1044;
          mbar_wait(bar_hw, 0);
#pragma unroll
          for (int p = 0; p < 8; p++) {
            const uint4 w = lds4(wa + p * 4096);
            const float s = __uint_as_float(__byte_perm(lds1(sa + p * 128), 0, sh));
            acc[0] += s * bf_lo(w.x); acc[1] += s * bf_hi(w.x); acc[2] += s * bf_lo(w.y); acc[3] += s * bf_hi(w.y);
            acc[4] += s * bf_lo(w.z); acc[5] += s * bf_hi(w.z); acc[6] += s * bf_lo(w.w); acc[7] += s * bf_hi(w.w);
          }
#pragma unroll
          for (int e = 0; e < 4; e++) {
            const bool up = lane & 16;
            acc[e] = (up ? acc[e + 4] : acc[e]) + __shfl_xor_sync(0xffffffffu, up ? acc[e] : acc[e + 4], 16);
          }
#pragma unroll
          for (int e = 0; e < 2; e++) {
            const bool up = lane & 8;
            acc[e] = (up ? acc[e + 2] : acc[e]) + __shfl_xor_sync(0xffffffffu, up ? acc[e] : acc[e + 2], 8);
          }
          {
            const bool up = lane & 4;
            acc[0] = (up ? acc[1] : acc[0]) + __shfl_xor_sync(0xffffffffu, up ? acc[0] : acc[1], 4);
          }
          sts1(base + 2 * GST_BYTES + warp * 2048 + ((lane & 3) * 8 + (lane >> 2)) * 4, __float_as_uint(acc[0]));
          bar_sync(1, 256);
          if (warp == 0) {
            float s = 0.f;
#pragma unroll
            for (int w8 = 0; w8 < 8; w8++) s += __uint_as_float(lds1(base + 2 * GST_BYTES + w8 * 2048 + lane * 4));
            st_relaxed(pmod, (__float_as_uint(s) & ~3u) | tag);
          }
          PROF(1, tid == 0, 3);
        }
      }
      cluster_wait();
      if (wg == 1) bar_arrive(2, 256);
    }

    float f0 = 0.f, f1 = 0.f;
    const uint32_t rempty = lane < 2 ? mapa(bempty, lane & 1) : 0;
    constexpr uint32_t GE = NSLOT * 8 + 32;
    float o[64], s[64];
#pragma unroll 1
    for (int ps = 0; ps < 3; ps++) {
      {
        const uint32_t xt = ps == 1 ? XT1 : XT2, wt = ps == 1 ? WT1 : WT2;
        const int nst = ps == 2 ? 28 : 14;
        if (ps == 0) {
          float ga[64], gb[64];
#pragma unroll
          for (int i = 0; i < 64; i++) { ga[i] = 0.f; gb[i] = 0.f; }
          uint32_t a[2][16];
          const uint32_t l = fresh_lane();
          uint32_t fa[4];
#pragma unroll
          for (int kk = 0; kk < 4; kk++) fa[kk] = (base + wg * 8192 + frag_offset(warp)) ^ (kk * 32);
          const uint32_t mt = par + (l & 3) * 16;
          auto fetch = [&](int i, uint32_t (&f)[16], uint32_t z) {
            mbar_wait(xfull + (i & 3) * 8, i >> 2);
#pragma unroll
            for (int kk = 0; kk < 4; kk++) ldmatrix4(fa[kk] + (i & 3) * GST_BYTES + z, f[4 * kk], f[4 * kk + 1], f[4 * kk + 2], f[4 * kk + 3]);
          };
          uint4 r0, r1;
          {
            const uint32_t t7 = (warp & 3) * 32 + l;
            const uint32_t* pm = g_modp + wg * DM + ((cj * 128 + t7 * 4) & (DM - 1));
            const uint32_t* pr = g_ln1 + (rb * 128 + warp * 16 + (l >> 2)) * 4;
            uint4 m0 = ld_relaxed4(pm), m1 = ld_relaxed4(pm + 2 * DM);
            r0 = ld_b128(pr); r1 = ld_b128(pr + 32);
            fetch(0, a[0], 0); fetch(1, a[1], 0);
            uint32_t n = 0;
            bool written = false;
#pragma unroll 1
            while (true) {
              uint32_t miss;
              asm volatile("{ .reg .pred p0, p1, p2, p3; .reg .b32 t, u;\n"
                           "lop3.b32 t, %1, %2, %19, 0x7e; lop3.b32 u, %3, %4, %19, 0x7e; or.b32 t, t, u; and.b32 t, t, 3; setp.ne.u32 p0, t, 0;\n"
                           "lop3.b32 t, %5, %6, %19, 0x7e; lop3.b32 u, %7, %8, %19, 0x7e; or.b32 t, t, u; and.b32 t, t, 3; setp.ne.u32 p1, t, 0;\n"
                           "setp.ne.u32 p2, %12, %19; setp.ne.u32 p3, %16, %19;\n"
                           "@p0 ld.relaxed.gpu.global.v4.u32 {%1, %2, %3, %4}, [%17];\n"
                           "@p1 ld.relaxed.gpu.global.v4.u32 {%5, %6, %7, %8}, [%17 + 8192];\n"
                           "@p2 ld.relaxed.gpu.global.v4.u32 {%9, %10, %11, %12}, [%18];\n"
                           "@p3 ld.relaxed.gpu.global.v4.u32 {%13, %14, %15, %16}, [%18 + 128];\n"
                           "or.pred p0, p0, p1; or.pred p2, p2, p3; vote.sync.any.pred p0, p0, 0xffffffff; vote.sync.any.pred p2, p2, 0xffffffff;\n"
                           "selp.u32 t, 1, 0, p0; selp.u32 u, 2, 0, p2; or.b32 %0, t, u; }"
                           : "=r"(miss), "+r"(m0.x), "+r"(m0.y), "+r"(m0.z), "+r"(m0.w), "+r"(m1.x), "+r"(m1.y), "+r"(m1.z), "+r"(m1.w),
                             "+r"(r0.x), "+r"(r0.y), "+r"(r0.z), "+r"(r0.w), "+r"(r1.x), "+r"(r1.y), "+r"(r1.z), "+r"(r1.w)
                           : "l"(pm), "l"(pr), "r"(tag) : "memory");
              if (!(miss & 1) && !written) {
                written = true;
                float c0 = untag_sum(m0.x, m1.x), c1 = untag_sum(m0.y, m1.y), c2 = untag_sum(m0.z, m1.z), c3 = untag_sum(m0.w, m1.w);
                if (wg) { c0 = 1.f + rbf(c0); c1 = 1.f + rbf(c1); c2 = 1.f + rbf(c2); c3 = 1.f + rbf(c3); }
                const uint32_t d = par + (t7 >> 2) * 64 + (t7 & 1) * 32 + (t7 & 2) * 2 + (wg ? 0 : 8);
                sts1(d, pack_bf(c0, c1));
                sts1(d + 16, pack_bf(c2, c3));
                mbar_arrive(bar_mod);
              }
              if (!miss) break;
              watchdog(n);
            }
          }
          const uint32_t zero = r0.w ^ tag;
          auto normalize = [&](uint32_t (&f)[16]) {
#pragma unroll
            for (int k = 0; k < 16; k += 2) { f[k] = ln_norm(f[k], r0.x, r0.y, r0.z); f[k + 1] = ln_norm(f[k + 1], r1.x, r1.y, r1.z); }
          };
          auto modulate = [&](int i, uint32_t (&f)[16]) {
#pragma unroll
            for (int kk = 0; kk < 4; kk++) {
              const uint4 m = lds4(mt + i * 256 + kk * 64);
              f[4 * kk] = MODUL(f[4 * kk], m.x, m.z); f[4 * kk + 1] = MODUL(f[4 * kk + 1], m.x, m.z);
              f[4 * kk + 2] = MODUL(f[4 * kk + 2], m.y, m.w); f[4 * kk + 3] = MODUL(f[4 * kk + 3], m.y, m.w);
            }
            keep(f);
            mbar_arrive_pred(xempty + (i & 3) * 8, l == 0);
          };
          auto publish = [&](int u, uint32_t (&f)[16]) {
#pragma unroll
            for (int kk = 0; kk < 4; kk++) stmatrix4(fa[kk] + OFF_STAGE + u * UNIT, f[4 * kk], f[4 * kk + 1], f[4 * kk + 2], f[4 * kk + 3]);
            __syncwarp();
            mbar_arrive_pred(bar_hpub + u * 8, l == 0);
          };
          auto multiply = [&](int i, uint32_t (&f)[16]) {
            mbar_wait(gfull + (i & 3) * 8, i >> 2);
            const uint64_t db = make_desc(base + (i & 3) * GST_BYTES + UNIT, 8192, 1024);
            wg_fence();
#pragma unroll
            for (int kk = 0; kk < 4; kk++) mma256_rs(ga, gb, f[4 * kk], f[4 * kk + 1], f[4 * kk + 2], f[4 * kk + 3], db + kk * 128);
            wg_commit();
          };
          auto next = [&](int i, uint32_t (&f)[16]) {
            wg_wait<1>();
            mbar_arrive_cl(rempty, GE + ((i + 2) & 3) * 8);
            uint32_t z = zero;
#pragma unroll
            for (int k = 0; k < 16; k += 2) asm volatile("lop3.b32 %0, %1, %2, %0, 0xA8;" : "+r"(z) : "r"(f[k]), "r"(f[k + 1]));
            fetch(i, f, z);
            normalize(f); modulate(i, f); multiply(i, f);
          };
          normalize(a[0]); normalize(a[1]);
          keep(a[0]); keep(a[1]);
          mbar_wait(bar_mod, 0);
          PROF(1, tid == 0, 2);
          modulate(0, a[0]); multiply(0, a[0]); publish(0, a[0]);
          modulate(1, a[1]); multiply(1, a[1]); publish(1, a[1]);
#pragma unroll 1
          for (int i = 2; i < NRS; i += 2) { next(i, a[0]); next(i + 1, a[1]); }
          wg_wait<1>();
          mbar_arrive_cl(rempty, GE + ((NRS + 2) & 3) * 8);
#pragma unroll 1
          for (int i = NRS; i < 14; i++) {
            mbar_wait(xfull + (i & 3) * 8, (i >> 2) & 1);
            mbar_wait(gfull + (i & 3) * 8, (i >> 2) & 1);
            const uint32_t xa = base + (i & 3) * GST_BYTES;
            const uint64_t da = make_desc(xa + wg * 8192, 16, 1024), db = make_desc(xa + UNIT, 8192, 1024);
            if (i == 13) bar_sync(2 + wg, 256);
            wg_fence();
#pragma unroll
            for (int kk = 0; kk < 4; kk++) mma256_ss(ga, gb, da + kk * 2, db + kk * 128, 1);
            wg_commit();
            if (i == 13) bar_arrive(3 - wg, 256);
            wg_wait<1>();
            uint32_t z = zero;
#pragma unroll
            for (int k = 0; k < 16; k += 2) asm volatile("lop3.b32 %0, %1, %2, %0, 0xA8;" : "+r"(z) : "r"(a[1][k]), "r"(a[1][k + 1]));
            mbar_arrive_cl(rempty, GE + ((i + 3) & 3) * 8 + z);
            mbar_arrive_pred(xempty + ((i + 3) & 3) * 8, l == 0 && i != NRS);
          }
          mbar_wait(xfull + 16, 1);
          wg_wait<0>();
          keep(ga); keep(gb);
#pragma unroll
          for (int i = 0; i < 64; i++) {
            asm volatile("mov.b32 %0, %1;" : "=f"(s[i]) : "f"(ga[i]));
            asm volatile("mov.b32 %0, %1;" : "=f"(o[i]) : "f"(gb[i]));
          }
        } else {
          float ga[64], gb[64];
#pragma unroll
          for (int i = 0; i < 64; i++) {
            asm volatile("mov.b32 %0, %1;" : "=f"(ga[i]) : "f"(s[i]));
            asm volatile("mov.b32 %0, %1;" : "=f"(gb[i]) : "f"(o[i]));
          }
#pragma unroll 1
          for (int i = 0; i < nst; i++) {
            mbar_wait(gfull + (i & 3) * 8, (i >> 2) & 1);
            const uint64_t da = make_desc(base + unit_of(xt, i & 3) + wg * 8192, 16, 1024), db = make_desc(base + unit_of(wt, i & 3), 8192, 1024);
            if (i == nst - 1) bar_sync(2 + wg, 256);
            wg_fence();
#pragma unroll
            for (int kk = 0; kk < 4; kk++) mma256_ss(ga, gb, da + kk * 2, db + kk * 128, kk ? 1 : i);
            wg_commit();
            if (i == nst - 1) bar_arrive(3 - wg, 256);
            wg_wait<1>();
            mbar_arrive_cl(rempty, GE + ((i + 3) & 3) * 8, i != 0);
            PROF(4, tid == 0 && (i & 3) == 0, 40 + (ps - 1) * 4 + i / 4);
          }
          wg_wait<0>();
          keep(ga); keep(gb);
#pragma unroll
          for (int i = 0; i < 64; i++) {
            asm volatile("mov.b32 %0, %1;" : "=f"(s[i]) : "f"(ga[i]));
            asm volatile("mov.b32 %0, %1;" : "=f"(o[i]) : "f"(gb[i]));
          }
        }
        mbar_arrive_cl(rempty, GE + (ps == 2 ? 24 : 8));
        if (ps == 2) break;
      }
      const uint32_t qw = base + wg * 8192, qt = QT >> (16 * ps), at = ps ? AT1 : AT0;
      {
        const uint32_t wt = ps ? WT1 : WT0;
        const uint64_t da0 = make_desc(qw + unit_of(qt, 2), 16, 1024), da1 = make_desc(qw + unit_of(qt, 3), 16, 1024);
        const uint64_t db0 = make_desc(base + unit_of(wt, 2), 8192, 1024), db1 = make_desc(base + unit_of(wt, 3), 8192, 1024);
        mbar_wait(gfull + 16, 1);
        bar_sync(2 + wg, 256);
        wg_fence();
#pragma unroll
        for (int kk = 0; kk < 4; kk++) mma_ss<1>(s, da0 + kk * 2, db0 + kk * 128, 1);
        wg_commit();
        mbar_wait(xfull + 24, 1);
        mbar_wait(gfull + 24, 1);
        wg_fence();
#pragma unroll
        for (int kk = 0; kk < 4; kk++) mma_ss<1>(s, da1 + kk * 2, db1 + kk * 128, 1);
        wg_commit();
        bar_arrive(3 - wg, 256);
        mbar_wait(ps == 0 ? bar_pread : bar_ofree + 8, 0);
        mbar_wait(bfull, 0);
        wg_wait<0>();
        keep(s);
        PROF(2, tid == 0, 8 + ps * 8);
        store_chunk<0>(s, qw + unit_of(qt, 0) + frag_offset(warp));
        store_chunk<1>(s, qw + unit_of(qt, 1) + frag_offset(warp));
        fence_async_smem();
        bar_sync(2 + wg, 256);
        wg_fence();
        issue_qk(s, qw + unit_of(qt, 0), qw + unit_of(qt, 1), base + unit_of(at, 0));
        wg_commit();
#pragma unroll
        for (int kk = 0; kk < 8; kk++) mma_ss<1>(o, (kk < 4 ? da0 : da1) + (kk & 3) * 2, (kk < 4 ? db0 : db1) + UNIT / 16 + (kk & 3) * 128, 1);
        wg_commit();
        bar_arrive(3 - wg, 256);
        wg_wait<1>();
        keep(s);
        mbar_arrive_cl(rempty, 0);
      }
      PROF(4, tid == 0 && ps == 1, 61);
      float l0 = 0.25f, l1 = 0.25f;
      auto step = [&](auto odd_c, const int j, uint32_t (&pw)[32], uint32_t (&pr)[32]) {
        constexpr bool ODD = decltype(odd_c)::value;
        const bool first = !ODD && (j & 2) == 0, last = ODD && j == 7;
        const uint32_t ph = (j >> 1) & 1;
        float i0, i1, a0, a1;
        if (first) { i0 = inv_quad_sum(l0); i1 = inv_quad_sum(l1); l0 = 0.f; l1 = 0.f; }
        bool redo = !ODD && (j | ps) == 0, again = false;
        while (true) {
          if (redo) {
            float m0 = fmaxf(s[0], s[1]), m1 = fmaxf(s[2], s[3]);
#pragma unroll
            for (int i = 1; i < 16; i++) { m0 = fmaxf(m0, fmaxf(s[4 * i], s[4 * i + 1])); m1 = fmaxf(m1, fmaxf(s[4 * i + 2], s[4 * i + 3])); }
            m0 = fmaxf(m0, __shfl_xor_sync(0xffffffffu, m0, 1)); m1 = fmaxf(m1, __shfl_xor_sync(0xffffffffu, m1, 1));
            m0 = fmaxf(m0, __shfl_xor_sync(0xffffffffu, m0, 2)); m1 = fmaxf(m1, __shfl_xor_sync(0xffffffffu, m1, 2));
            m0 *= SCL2; m1 *= SCL2;
            if (!first) {
              m0 = fmaxf(m0, f0); m1 = fmaxf(m1, f1);
              const float c0 = ex2(f0 - m0), c1 = ex2(f1 - m1);
              l0 *= c0; l1 *= c1;
              wg_wait<0>();
              keep(o);
#pragma unroll
              for (int i = 0; i < 16; i++) { o[4 * i] *= c0; o[4 * i + 1] *= c0; o[4 * i + 2] *= c1; o[4 * i + 3] *= c1; }
            }
            f0 = m0; f1 = m1;
          }
          float b0 = 0.f, b1 = 0.f;
          a0 = 0.f; a1 = 0.f;
#pragma unroll
          for (int i = 0; i < 16; i++) {
            const float e0 = ex2(fmaf(s[4 * i], SCL2, -f0)), e1 = ex2(fmaf(s[4 * i + 1], SCL2, -f0));
            const float e2 = ex2(fmaf(s[4 * i + 2], SCL2, -f1)), e3 = ex2(fmaf(s[4 * i + 3], SCL2, -f1));
            a0 += e0; b0 += e1; a1 += e2; b1 += e3;
            pw[2 * i] = pack_bf(e0, e1); pw[2 * i + 1] = pack_bf(e2, e3);
            if (i == VREL) {
#pragma unroll
              for (int k = 0; k < 2 * VREL + 2; k++) asm volatile("" : "+r"(pw[k])::"memory");
              mbar_wait(bar_mod, 0);
              wg_wait<0>();
              mbar_arrive_cl(rempty, ODD ? 16 : (j ? 0 : GE + 16), !again);
              if (!ODD) mbar_arrive_cl(rempty, GE + 24, !again && j == 0);
#pragma unroll
              for (int k = 4 * VREL + 4; k < 64; k++) asm volatile("" : "+f"(s[k])::"memory");
            }
          }
          a0 += b0; a1 += b1;
          if (redo) break;
          redo = __any_sync(0xffffffffu, !(a0 + a1 < 0x1p70f));
          if (first) {
            uint32_t m0 = __ballot_sync(0xffffffffu, a0 > 0x1p-50f), m1 = __ballot_sync(0xffffffffu, a1 > 0x1p-50f);
            m0 |= m0 >> 1; m1 |= m1 >> 1; m0 |= m0 >> 2; m1 |= m1 >> 2;
            redo = redo || (m0 & m1 & 0x11111111u) != 0x11111111u;
          }
          if (!redo) break;
          again = true;
        }
        l0 += a0; l1 += a1;
        keep(pw);
        keep(o);
        const uint32_t qo = qt >> (j ? 0 : 8);
        if (first) store_chunk<0>(o, i0, i1, qw + unit_of(qo, 0) + frag_offset(warp));
        keep(o);
        mbar_wait(bfull + (ODD ? 24 : 8), ph);
        bar_sync(2 + wg, 256);
        if (!last) {
          const uint32_t qn = qt >> (j >= 3 ? 8 : 0);
          wg_fence();
          issue_qk(s, qw + unit_of(qn, 0), qw + unit_of(qn, 1), base + unit_of(at, ODD ? 3 : 1));
          wg_commit();
          mbar_wait(bfull + (ODD ? 0 : 16), ODD ? ph ^ 1 : ph);
        }
        if (first) { store_chunk<1>(o, i0, i1, qw + unit_of(qo, 1) + frag_offset(warp)); keep(o); }
        wg_fence();
        issue_pv(o, pw, base + unit_of(at, ODD ? (last ? 3 : 0) : 2), !first);
        wg_commit();
        bar_arrive(3 - wg, 256);
        wg_wait<1>();
        keep(s);
        mbar_arrive_cl(rempty, ODD ? 24 : 8, !last);
        if (first) { fence_async_smem(); mbar_arrive_pred(bar_ofull + wg * 8, j); }
        PROF(4, tid == 0 && ps == 1, 51 + j);
      };
      uint32_t pa[32], pb[32];
#pragma unroll 1
      for (int j = 0; j < 8; j += 2) {
        step(std::false_type{}, j, pa, pb);
        step(std::true_type{}, j + 1, pb, pa);
      }
      {
        const float i0 = inv_quad_sum(l0), i1 = inv_quad_sum(l1);
        wg_wait<0>();
        keep(o);
        mbar_arrive_cl(rempty, 24);
        store_chunk<0>(o, i0, i1, qw + unit_of(qt, 2) + frag_offset(warp));
        store_chunk<1>(o, i0, i1, qw + unit_of(qt, 3) + frag_offset(warp));
        fence_async_smem();
        mbar_arrive(bar_ofull + 16 + wg * 8);
      }
      PROF(2, tid == 0, 10 + ps * 8);
    }

    const int ln = fresh_lane(), g = ln >> 2, tq = ln & 3, ct = warp * 32 + ln;
    const bool lane0 = ln == 0;
    const int lrow0 = warp * 16 + g;
    const int grow0 = rb * 128 + lrow0;
    const uint32_t res = base + OFF_RES, trow = res + wg * 8192 + frag_offset(warp);
    uint32_t xr[32];
    uint4 sv[4], own;
    uint32_t* sp[4];
#pragma unroll
    for (int k = 0; k < 4; k++) sp[k] = g_stats + ((((tq >> 1) * 4 + k) ^ cj) * SEQ + grow0 + (tq & 1) * 8) * 4;
    {
      const uint64_t da = make_desc(base + wg * 8192, 16, 1024), db = make_desc(base, 8192, 1024);
      constexpr int U = UNIT / 16;
#define HALF_STAGE(acc, xu, wu) _Pragma("unroll") for (int kk = 0; kk < 4; kk++) mma_ss<1>(acc, da + (xu) * U + kk * 2, db + (wu) * U + kk * 128, 1)
      PROF(10, ct == PT, 19); STAMP(0);
      cluster_arrive();
      mbar_wait(gfull, 1);
      mbar_wait(gfull + 8, 1);
      bar_sync(2 + wg, 256);
      wg_fence();
      HALF_STAGE(o, 7, 1);
      HALF_STAGE(o, 8, 3);
      wg_commit();
      STAMP(16);
      mbar_wait(gfull + 16, 1);
      STAMP(17);
      wg_fence();
      HALF_STAGE(o, 6, 11);
      wg_commit();
      bar_arrive(3 - wg, 256);
      mbar_wait(bar_par, 0);
      uint32_t* xo = g_xch + ((size_t)b * 8 * 256 + ct) * 4;
      const uint32_t* xi = g_xch + ((size_t)(b ^ 2) * 8 * 256 + ct) * 4;
      const uint32_t par1 = (~lds1(par + PAR_CONST + 4) & 1) << 16;
      uint32_t ga[16];
      uint4 bw[8];
#define LOAD_PAR _Pragma("unroll") for (int i = 0; i < 8; i++) {                                                               \
        ga[2 * i] = lds1(par + PAR_T2 + i * 128 + tq * 16 + 12); ga[2 * i + 1] = lds1(par + PAR_T2 + i * 128 + 64 + tq * 16 + 12); \
        bw[i] = lds4(par + PAR_T1 + i * 64 + tq * 16);                                                                          \
        if (!(g & 1)) { bw[i].x = 0x3f803f80u; bw[i].y = 0x3f803f80u; }                                                         \
      }
      if (PPOS == 0) LOAD_PAR
      wg_wait<1>();
      mbar_arrive_pred(bar_rel, lane0);
      wg_wait<0>();
      keep(o);
      mbar_arrive_pred(bar_ring, lane0);
      PROF(8, ct == PT, 20); STAMP(1);
#define SEND(i) st_b128(xo + (i) * 1024, (pack_bf(o[8 * (i)], o[8 * (i) + 1]) & ~0x10000u) | par1, pack_bf(o[8 * (i) + 2], o[8 * (i) + 3]), \
                        pack_bf(o[8 * (i) + 4], o[8 * (i) + 5]), pack_bf(o[8 * (i) + 6], o[8 * (i) + 7]))
#pragma unroll
      for (int i = 0; i < NS1; i++) SEND(i);
      PROF(8, ct == PT, 21); STAMP(2);
      bar_sync(2 + wg, 256);
      wg_fence();
      HALF_STAGE(s, 7, 0);
      HALF_STAGE(s, 8, 2);
      HALF_STAGE(s, 6, 10);
      wg_commit();
      bar_arrive(3 - wg, 256);
      STAMP(18);
      mbar_wait(gfull + 24, 1);
#pragma unroll
      for (int i = NS1; i < 8; i++) SEND(i);
      uint4 v[8];
#pragma unroll
      for (int i = 0; i < 4; i++) v[i] = ld_b128(xi + i * 1024);
      if (PPOS == 1) LOAD_PAR
      STAMP(19);
      mbar_wait(bar_xres, 0);
      wg_wait<0>();
      mbar_arrive_pred(bar_ring + 8, lane0);
      bar_sync(2 + wg, 256);
      STAMP(20);
#pragma unroll
      for (int i = 4; i < 8; i++) v[i] = ld_b128(xi + i * 1024);
      mbar_wait(bar_xres, 0);
      wg_fence();
      HALF_STAGE(s, 9, 4);
      wg_commit();
      mbar_wait(bar_rx, 0);
      wg_fence();
      HALF_STAGE(s, 1, 5);
      wg_commit();
      bar_arrive(3 - wg, 256);
      STAMP(21);
      wg_wait<0>();
      keep(s);
      mbar_arrive_pred(bar_ring + 16, lane0);
      PROF(10, ct == PT, 23); STAMP(4);
#pragma unroll
      for (int i = 0; i < 16; i += 2) ldmatrix4((trow ^ ((i & 7) << 4)) + (i >> 3) * 16384, xr[2 * i], xr[2 * i + 1], xr[2 * i + 2], xr[2 * i + 3]);
      if (PPOS == 2) LOAD_PAR
      uint32_t pk[32];
      pack_p(s, pk);
      keep(pk);
      {
        uint32_t n = 0, miss;
        do {
          miss = 0;
#pragma unroll
          for (int i = 0; i < 8; i++) miss |= v[i].x ^ par1;
          miss = __any_sync(0xffffffffu, miss & 0x10000u);
          if (miss) {
#pragma unroll
            for (int i = 0; i < 8; i++)
              asm volatile("{ .reg .pred p; .reg .b32 t; xor.b32 t, %0, %5; and.b32 t, t, 0x10000; setp.ne.u32 p, t, 0;\n"
                           "@p ld.relaxed.gpu.global.v4.u32 {%0, %1, %2, %3}, [%4]; }"
                           : "+r"(v[i].x), "+r"(v[i].y), "+r"(v[i].z), "+r"(v[i].w) : "l"(xi + i * 1024), "r"(par1) : "memory");
          }
          watchdog(n);
        } while (miss);
      }
      PROF(8, ct == PT, 22); STAMP(3);
#pragma unroll
      for (int k = 0; k < 4; k++) sv[k] = ESV ? ld_b128(sp[k]) : make_uint4(0, 0, 0, 0);
      float ds[4] = {0.f, 0.f, 0.f, 0.f}, dl[4] = {0.f, 0.f, 0.f, 0.f}, q0[4] = {0.f, 0.f, 0.f, 0.f}, q1[4] = {0.f, 0.f, 0.f, 0.f};
#pragma unroll
      for (int i = 0; i < 8; i++) {
        const uint32_t u0 = hfma2(ga[2 * i], hadd2(pk[4 * i], v[i].x & ~0x10000u), xr[4 * i]);
        const uint32_t u1 = hfma2(ga[2 * i], hadd2(pk[4 * i + 1], v[i].y), xr[4 * i + 1]);
        const uint32_t u2 = hfma2(ga[2 * i + 1], hadd2(pk[4 * i + 2], v[i].z), xr[4 * i + 2]);
        const uint32_t u3 = hfma2(ga[2 * i + 1], hadd2(pk[4 * i + 3], v[i].w), xr[4 * i + 3]);
        xr[4 * i] = u0; xr[4 * i + 1] = u1; xr[4 * i + 2] = u2; xr[4 * i + 3] = u3;
        mma16816(ds, u0, u1, u2, u3, bw[i].x, bw[i].y);
        mma16816(dl, u0, u1, u2, u3, bw[i].z, bw[i].w);
        mma16816(q0, u0, u1, u2, u3, u0, u2);
        mma16816(q1, u0, u1, u2, u3, u1, u3);
      }
      const float sqa = __shfl_sync(0xffffffffu, (g & 1) ? q0[1] : q0[0], g * 4 + (g >> 1));
      const float sqb = __shfl_sync(0xffffffffu, (g & 1) ? q1[3] : q1[2], g * 4 + (g >> 1));
      own = (tq & 1) ? make_uint4(__float_as_uint(ds[2]), __float_as_uint(sqb), __float_as_uint(ds[3] + dl[3]), tag)
                                 : make_uint4(__float_as_uint(ds[0]), __float_as_uint(sqa), __float_as_uint(ds[1] + dl[1]), tag);
      if (tq < 2) st_b128(sp[0], own.x, own.y, own.z, own.w);
    }
    PROF(8, ct == PT, 29); STAMP(5);
    uint32_t mm, ih, il;
    float rbest;
    uint32_t wf[128];
    const uint32_t frow = (ln & 7) + (ln >> 4) * 8;
    const uint32_t wfo = base + (warp & 1) * 8192 + frow * 64 + ((((ln >> 3) & 1) ^ ((frow >> 1) & 3)) << 4);
#define LOAD_WF(m) _Pragma("unroll") for (int f = 0; f < 16; f++) {                                                   \
      const int r = ((f >> 1) * 4 + (m) * 2 + (f & 1)) * 4;                                                           \
      ldmatrix4t(((wfo + unit_of((m) ? FT_U : FT_G, warp >> 1)) ^ ((f & 1) * 32)) + (f >> 1) * 1024, wf[r], wf[r + 1], wf[r + 2], wf[r + 3]); \
    }
    bool early, wait1;
    {
#pragma unroll
      for (int i = 0; i < 16; i += 2) stmatrix4((trow ^ ((i & 7) << 4)) + (i >> 3) * 16384, xr[2 * i], xr[2 * i + 1], xr[2 * i + 2], xr[2 * i + 3]);
      const uint4 cst = lds4(par + PAR_CONST);
      const float A1 = __uint_as_float(cst.x), A2 = __uint_as_float(cst.z);
      uint32_t n = 0;
      early = false; wait1 = false;
#pragma unroll 1
      while (true) {
        uint32_t miss;
        asm volatile("{ .reg .pred p0, p1, p2, p3; .reg .b64 u, v; .reg .b128 w;\n"
                     "setp.ge.u32 p0, %22, 2; setp.ne.and.u32 p0, %4, %21, p0; setp.ne.u32 p1, %8, %21; setp.ne.u32 p2, %12, %21; setp.ne.u32 p3, %16, %21;\n"
                     "@p0 ld.relaxed.gpu.global.v4.u32 {%1, %2, %3, %4}, [%17];\n"
                     "@p1 ld.relaxed.gpu.global.v4.u32 {%5, %6, %7, %8}, [%18];\n"
                     "@p2 ld.relaxed.gpu.global.v4.u32 {%9, %10, %11, %12}, [%19];\n"
                     "@p3 ld.relaxed.gpu.global.v4.u32 {%13, %14, %15, %16}, [%20];\n"
                     "or.pred p0, p0, p1; or.pred p2, p2, p3; or.pred p0, p0, p2; vote.sync.any.pred p0, p0, 0xffffffff; selp.u32 %0, 1, 0, p0; }"
                     : "=r"(miss), "+r"(sv[0].x), "+r"(sv[0].y), "+r"(sv[0].z), "+r"(sv[0].w), "+r"(sv[1].x), "+r"(sv[1].y), "+r"(sv[1].z), "+r"(sv[1].w),
                       "+r"(sv[2].x), "+r"(sv[2].y), "+r"(sv[2].z), "+r"(sv[2].w), "+r"(sv[3].x), "+r"(sv[3].y), "+r"(sv[3].z), "+r"(sv[3].w)
                     : "l"(sp[0]), "l"(sp[1]), "l"(sp[2]), "l"(sp[3]), "r"(tag), "r"(tq) : "memory");
        if (!miss) break;
        wait1 = true;
        if (!early && (b >= NFFN || __all_sync(0xffffffffu, mbar_test(bar_box + (warp >> 1) * 8, 0)))) {
          early = true;
          LOAD_WF(0);
          __syncwarp();
          mbar_arrive_pred(bar_gate, lane0);
        }
        watchdog(n);
      }
      const uint4 v0 = tq < 2 ? own : sv[0], v1 = sv[1], v2 = sv[2], v3 = sv[3];
      PROF(8, ct == PT, 30); STAMP(6);
      float su = (__uint_as_float(v0.x) + __uint_as_float(v1.x)) + (__uint_as_float(v2.x) + __uint_as_float(v3.x));
      float sq = (__uint_as_float(v0.y) + __uint_as_float(v1.y)) + (__uint_as_float(v2.y) + __uint_as_float(v3.y));
      float dt = (__uint_as_float(v0.z) + __uint_as_float(v1.z)) + (__uint_as_float(v2.z) + __uint_as_float(v3.z));
      su += __shfl_xor_sync(0xffffffffu, su, 2); sq += __shfl_xor_sync(0xffffffffu, sq, 2); dt += __shfl_xor_sync(0xffffffffu, dt, 2);
      const float m = su * (1.f / DM);
      float mb, sd;
      ln_scalars(m, fmaxf(sq * (1.f / DM) - m * m, 0.f), mb, sd);
      const float inv = rcp(sd);
      rbest = (dt - mb * A1) * inv + A2;
      mm = pack_bf(mb, mb);
      ih = pack_bf(inv, inv);
      const float lo = inv - bf_lo(ih);
      il = pack_bf(lo, lo);
    }
    int ibest;
    {
      const uint32_t bits = __float_as_uint(rbest);
      const uint32_t key = (((int)bits < 0 ? ~bits : bits | 0x80000000u) & ~0x1ffu) | ((127 - lrow0 - (tq & 1) * 8) << 2) | tag;
      sts1(par + PAR_RED + warp * 4, __reduce_max_sync(0xffffffffu, key));
      PROF(8, ct == PT, 38); STAMP(7);
      uint32_t waited;
      asm volatile("{ .reg .pred p, q; setp.ne.u32 p, %1, 0; barrier.cta.red.or.pred q, 1, 256, p; selp.u32 %0, 1, 0, q; }" : "=r"(waited) : "r"((uint32_t)(wait1 && (wg || CW0))) : "memory");
      const uint4 ka = lds4(par + PAR_RED), kb = lds4(par + PAR_RED + 16);
      const uint32_t k2 = max(max(max(ka.x, ka.y), max(ka.z, ka.w)), max(max(kb.x, kb.y), max(kb.z, kb.w)));
      if (ct == 0 && ((cj & CWM) == 0 || (CWL && !waited))) st_relaxed(g_cand + rb, k2);
      ibest = 127 - ((k2 >> 2) & 127);
    }
    PROF(8, ct == PT, 39); STAMP(8);
    if ((ibest >> 4) == warp) {
      const int src = (ibest & 7) * 4 + ((ibest >> 3) & 1), ch = g * 2;
      const uint32_t cm = __shfl_sync(0xffffffffu, mm, src), ch_ = __shfl_sync(0xffffffffu, ih, src), cl = __shfl_sync(0xffffffffu, il, src);
      const uint32_t xa = res + (ch >> 3) * 16384 + ibest * 128 + (((ch & 7) ^ (ibest & 7)) << 4) + tq * 4;
      const uint32_t x0 = lds1(xa), x1 = lds1(xa ^ 16);
      const uint2 p0 = lds2(par + PAR_T2 + ch * 64 + tq * 16), p1 = lds2(par + PAR_T2 + ch * 64 + 64 + tq * 16);
      uint32_t* dst = g_row + rb * 2 * DM + cj * 128 + ln * 4;
      st_pairs(dst, ln_mod(x0, cm, ch_, cl, p0.x, p0.y), ln_mod(x1, cm, ch_, cl, p1.x, p1.y), tag);
      st_pairs(dst + DM, x0, x1, tag);
      __syncwarp();
    }
    PROF(8, ct == PT, 37); STAMP(9);
    const bool cand = (ibest >> 4) == warp;
    auto out_tile = [&]() {
      const uint32_t mm0 = __shfl_sync(0xffffffffu, mm, ln & ~1), mm1 = __shfl_sync(0xffffffffu, mm, ln | 1);
      const uint32_t ih0 = __shfl_sync(0xffffffffu, ih, ln & ~1), ih1 = __shfl_sync(0xffffffffu, ih, ln | 1);
      const uint32_t il0 = __shfl_sync(0xffffffffu, il, ln & ~1), il1 = __shfl_sync(0xffffffffu, il, ln | 1);
#pragma unroll 1
      for (int hf = 0; hf < 2; hf++) {
        uint32_t x[16];
#pragma unroll
        for (int i = 0; i < 8; i += 2) ldmatrix4((trow ^ (i << 4)) + hf * 16384, x[2 * i], x[2 * i + 1], x[2 * i + 2], x[2 * i + 3]);
#pragma unroll
        for (int i = 0; i < 8; i++) {
          const uint4 pv = lds4(par + PAR_T2 + (hf * 8 + i) * 64 + tq * 16);
          x[2 * i] = hadd2(x[2 * i], hmul2(pv.z, ln_mod(x[2 * i], mm0, ih0, il0, pv.x, pv.y)));
          x[2 * i + 1] = hadd2(x[2 * i + 1], hmul2(pv.z, ln_mod(x[2 * i + 1], mm1, ih1, il1, pv.x, pv.y)));
        }
#pragma unroll
        for (int i = 0; i < 8; i += 2) stmatrix4((trow ^ (i << 4)) + hf * 16384, x[2 * i], x[2 * i + 1], x[2 * i + 2], x[2 * i + 3]);
      }
      if (!cand) fence_async_smem();
      __syncwarp();
      if (LNS == 0 && !cand && elect_one()) {
        tma2d_store(&maps.out, res + warp * 2048, cj * 128, rb * 128 + warp * 16);
        tma2d_store(&maps.out, res + 16384 + warp * 2048, cj * 128 + 64, rb * 128 + warp * 16);
        asm volatile("cp.async.bulk.commit_group;" ::: "memory");
      }
    };
    if (LNP == 1 || (LNP == 2 && b >= NFFN)) out_tile();
    uint32_t wd[64];
    const uint32_t wda = base + unit_of(FT_D, warp >> 1) + (warp & 1) * 8192 + frow * 128 + ((((ln >> 3) & 1) ^ (ln & 7)) << 4);
#define LOAD_WD(f) ldmatrix4t((wda ^ ((((f) >> 1) & 3) * 32)) + ((f) >> 3) * 4096 + ((f) & 1) * 2048, wd[4 * (f)], wd[4 * (f) + 1], wd[4 * (f) + 2], wd[4 * (f) + 3])
    if (!early) {
      if (b < NFFN) mbar_wait(bar_box + (warp >> 1) * 8, 0);
      LOAD_WF(0);
      __syncwarp();
      mbar_arrive_pred(bar_gate, lane0);
    }
    if (b < NFFN) {
      const uint32_t own = base + unit_of(FT_G, warp >> 1) + (warp & 1) * 8192;
      mbar_wait(bar_box + (4 + (warp >> 1)) * 8, 0);
      LOAD_WF(1);
      uint32_t* const ydst = g_ypart + ((size_t)(warp * 16 + tq * 2) * NFFN + b) * 8 + g;
      if (LNP == 2) out_tile();
      PROF(8, ct == PT, 31); STAMP(10);
      mbar_wait(bar_box + (8 + (warp >> 1)) * 8, 0);
#pragma unroll
      for (int f = 0; f < WDE; f++) LOAD_WD(f);
      STAMP(11);
      mbar_wait(bar_sel, 0);
      PROF(8, ct == PT, 33); STAMP(12);
      if (LNS == 1 && !cand && elect_one()) {
        tma2d_store(&maps.out, res + warp * 2048, cj * 128, rb * 128 + warp * 16);
        tma2d_store(&maps.out, res + 16384 + warp * 2048, cj * 128 + 64, rb * 128 + warp * 16);
        asm volatile("cp.async.bulk.commit_group;" ::: "memory");
      }
      float d[8][4];
#pragma unroll
      for (int i = 0; i < 4; i++) { d[i][0] = 0.f; d[i][1] = 0.f; d[i][2] = 0.f; d[i][3] = 0.f; }
#pragma unroll
      for (int ks = 0; ks < 8; ks++) {
        const uint2 hb = lds2(own + 256 + ks * 32 + tq * 8);
#pragma unroll
        for (int mt = 0; mt < 4; mt++) {
          const int r = ks * 16 + mt * 4;
          mma16816(d[mt], wf[r], wf[r + 1], wf[r + 2], wf[r + 3], hb.x, hb.y);
        }
      }
      sts2(own + (tq * 8 + g) * 8, __float_as_uint((tq & 2) ? ((tq & 1) ? d[1][2] : d[1][0]) : ((tq & 1) ? d[0][2] : d[0][0])),
           __float_as_uint((tq & 2) ? ((tq & 1) ? d[3][2] : d[3][0]) : ((tq & 1) ? d[2][2] : d[2][0])));
      bar_sync(1, 256);
      uint32_t ab[4];
      {
        float G = 0.f, U = 0.f;
        uint2 pv[8];
#pragma unroll
        for (int w8 = 0; w8 < 8; w8++) pv[w8] = lds2(base + ln * 8 + ((FT_G >> (w8 >> 1) * 4) & 15) * UNIT + (w8 & 1) * 8192);
#pragma unroll
        for (int w8 = 0; w8 < 8; w8 += 2) {
          G += __uint_as_float(pv[w8].x) + __uint_as_float(pv[w8 + 1].x);
          U += __uint_as_float(pv[w8].y) + __uint_as_float(pv[w8 + 1].y);
        }
#pragma unroll
        for (int f = WDE; f < 16; f++) LOAD_WD(f);
        const float act = rbf(silu_f(rbf(G))) * rbf(U);
        const uint32_t pk = pack_bf(act, __shfl_down_sync(0xffffffffu, act, 1));
#pragma unroll
        for (int i = 0; i < 4; i++) ab[i] = __shfl_sync(0xffffffffu, pk, i * 8 + tq * 2);
      }
      PROF(8, ct == PT, 34); STAMP(13);
#pragma unroll
      for (int mt = 0; mt < 8; mt++) {
        d[mt][0] = 0.f; d[mt][1] = 0.f; d[mt][2] = 0.f; d[mt][3] = 0.f;
        mma16816(d[mt], wd[mt * 8], wd[mt * 8 + 1], wd[mt * 8 + 2], wd[mt * 8 + 3], ab[0], ab[1]);
        mma16816(d[mt], wd[mt * 8 + 4], wd[mt * 8 + 5], wd[mt * 8 + 6], wd[mt * 8 + 7], ab[2], ab[3]);
      }
#pragma unroll
      for (int i = 0; i < 4; i++) {
        const int m4 = (i >> 1) * 4, e = (i & 1) * 2;
        const float y = (tq & 2) ? ((tq & 1) ? d[m4 + 3][e] : d[m4 + 2][e]) : ((tq & 1) ? d[m4 + 1][e] : d[m4][e]);
        st_relaxed(ydst + (m4 * 2 + (i & 1)) * NFFN * 8, tagf(y, tag));
      }
      PROF(8, ct == PT, 35); STAMP(14);
    }
    mbar_wait(bar_sel, 0);
    mbar_arrive_pred(bar_win, ct == 0);
    if ((LNS == 2 || (LNS == 1 && b >= NFFN)) && !cand && elect_one()) {
      tma2d_store(&maps.out, res + warp * 2048, cj * 128, rb * 128 + warp * 16);
      tma2d_store(&maps.out, res + 16384 + warp * 2048, cj * 128 + 64, rb * 128 + warp * 16);
      asm volatile("cp.async.bulk.commit_group;" ::: "memory");
    }
    const int iwin = lds1(par + PAR_CONST + 60) & 0x7ff;
    if (LNP == 0) out_tile();
    if (cand) {
      const int wrow0 = warp * 16;
#pragma unroll 2
      for (int p = 0; p < 8; p++) {
        const int row = 2 * p + (ln >> 4), ch = ln & 15;
        const uint4 v = lds4(res + (ch >> 3) * 16384 + (wrow0 + row) * 128 + (((ch & 7) ^ (row & 7)) << 4));
        if (rb * 128 + wrow0 + row != iwin) *reinterpret_cast<uint4*>(P.out + (size_t)(rb * 128 + wrow0 + row) * DM + cj * 128 + ch * 8) = v;
      }
    }
    asm volatile("cp.async.bulk.wait_group.read 0;" ::: "memory");
    PROF(8, ct == PT, 11); STAMP(15);
    cluster_wait();
  }
}

typedef CUresult (*EncodeFn)(CUtensorMap*, CUtensorMapDataType, cuuint32_t, void*, const cuuint64_t*, const cuuint64_t*,
                             const cuuint32_t*, const cuuint32_t*, CUtensorMapInterleave, CUtensorMapSwizzle,
                             CUtensorMapL2promotion, CUtensorMapFloatOOBfill);

void map2d(EncodeFn enc, CUtensorMap* m, const void* p, uint64_t rows, uint64_t cols, uint32_t brows) {
  cuuint64_t dims[2] = {cols, rows}, strides[1] = {cols * 2};
  cuuint32_t box[2] = {64, brows}, es[2] = {1, 1};
  enc(m, CU_TENSOR_MAP_DATA_TYPE_BFLOAT16, 2, const_cast<void*>(p), dims, strides, box, es, CU_TENSOR_MAP_INTERLEAVE_NONE,
      CU_TENSOR_MAP_SWIZZLE_128B, CU_TENSOR_MAP_L2_PROMOTION_L2_256B, CU_TENSOR_MAP_FLOAT_OOB_FILL_NONE);
}
void map2d_narrow(EncodeFn enc, CUtensorMap* m, const void* p, uint64_t rows, uint64_t cols, uint32_t brows) {
  cuuint64_t dims[2] = {cols, rows}, strides[1] = {cols * 2};
  cuuint32_t box[2] = {32, brows}, es[2] = {1, 1};
  enc(m, CU_TENSOR_MAP_DATA_TYPE_BFLOAT16, 2, const_cast<void*>(p), dims, strides, box, es, CU_TENSOR_MAP_INTERLEAVE_NONE,
      CU_TENSOR_MAP_SWIZZLE_64B, CU_TENSOR_MAP_L2_PROMOTION_L2_64B, CU_TENSOR_MAP_FLOAT_OOB_FILL_NONE);
}
void map3d(EncodeFn enc, CUtensorMap* m, const void* p, uint64_t rows, uint64_t cols, uint32_t brows, uint32_t nch) {
  cuuint64_t dims[3] = {64, rows, cols / 64}, strides[2] = {cols * 2, 128};
  cuuint32_t box[3] = {64, brows, nch}, es[3] = {1, 1, 1};
  enc(m, CU_TENSOR_MAP_DATA_TYPE_BFLOAT16, 3, const_cast<void*>(p), dims, strides, box, es, CU_TENSOR_MAP_INTERLEAVE_NONE,
      CU_TENSOR_MAP_SWIZZLE_128B, CU_TENSOR_MAP_L2_PROMOTION_L2_256B, CU_TENSOR_MAP_FLOAT_OOB_FILL_NONE);
}

}

extern "C" void kernel_launch(void* const* d_in, const int* in_sizes, int n_in, void* d_out, int out_size) {
  (void)in_sizes; (void)n_in; (void)out_size;
  static EncodeFn enc = nullptr;
  if (!enc) {
    void* fn = nullptr;
    cudaDriverEntryPointQueryResult st;
    cudaGetDriverEntryPoint("cuTensorMapEncodeTiled", &fn, cudaEnableDefault, &st);
    enc = (EncodeFn)fn;
    cudaFuncSetAttribute(fused_kernel, cudaFuncAttributeMaxDynamicSharedMemorySize, SMEM_BYTES);
  }
  Maps maps;
  map2d(enc, &maps.x, d_in[0], SEQ, DM, 128);
  map2d(enc, &maps.out, d_out, SEQ, DM, 16);
  map3d(enc, &maps.wq, d_in[3], DM, NQ, 64, 2);
  map3d(enc, &maps.k, d_in[1], 4 * SK, 128, 128, 1);
  map3d(enc, &maps.v, d_in[2], 4 * SK, 128, 128, 1);
  map3d(enc, &maps.wo, d_in[4], NQ, DM, 64, 2);
  map2d_narrow(enc, &maps.wg, d_in[7], DM, FF, 256);
  map2d_narrow(enc, &maps.wu, d_in[8], DM, FF, 256);
  map3d(enc, &maps.wd, d_in[9], FF, DM, 32, 4);
  map2d_narrow(enc, &maps.wm, d_in[11], DM, NMOD, 256);
  Ptrs p;
  p.x = (const __nv_bfloat16*)d_in[0];
  p.w_r = (const __nv_bfloat16*)d_in[6];
  p.w_gate = (const __nv_bfloat16*)d_in[7];
  p.w_up = (const __nv_bfloat16*)d_in[8];
  p.w_down = (const __nv_bfloat16*)d_in[9];
  p.c = (const __nv_bfloat16*)d_in[10];
  p.w_mod = (const __nv_bfloat16*)d_in[11];
  p.out = (__nv_bfloat16*)d_out;
  fused_kernel<<<NMAIN + NHELP, 384, SMEM_BYTES>>>(maps, p);
}
```

```cpp
#include <cuda_runtime.h>
#include <cuda_bf16.h>
#include <cuda.h>
#include <stdint.h>
#include <type_traits>

#define HD 2
#define HDX 2
#define XF 4
#define XE 32
#define XR 0
#define NRS 8
#define FPACE 3
#define GOST 20
#define WB 3
#define WN 24
#define RES0 17
#define RES1 20
#define HU 32
#define NS1 6
#define PG0 0
#define PSL 0
#define CWM 7
#define WDE 16
#define CWL 1
#define CW0 0
#define ESV 1
#define PPOS 1
#define FB0 0
#define FB2 8
#define OPS 8192
#define OFL 0
#define ODS 8
#define MODUL hfma2
#define VREL 7
#define E0 3

namespace {

constexpr int SEQ = 2048, DM = 1024, NQ = 4096, SK = 2048, WIN = 512, FF = 3584, NMOD = 6144;
constexpr int NMAIN = 128, NHELP = 4, NFFN = 112;
constexpr int NSLOT = 4, SLOT_BYTES = 32768, UNIT = 16384, GST_BYTES = 3 * UNIT;
constexpr uint32_t XT1 = 0xDCBA, XT2 = 0x9687;
constexpr uint32_t WT0 = 0xA741, WT1 = 0x7420, WT2 = 0x4A20;
constexpr uint32_t AT0 = WT1, AT1 = WT2;
constexpr uint32_t QT = 0xDC9696DC;
constexpr int OFF_STAGE = 12 * UNIT;
constexpr uint32_t FT_G = 0x07B3, FT_U = 0xA628, FT_D = 0x5149;
constexpr int OFF_RES = 12 * UNIT;
constexpr int OFF_PAR = 14 * UNIT;
constexpr int OFF_BAR = OFF_PAR + 2528;
constexpr int SMEM_BYTES = OFF_BAR + 544;
static_assert(SMEM_BYTES <= 232448, "smem");

constexpr int PAR_T1 = 0;
constexpr int PAR_T2 = 512;
constexpr int PAR_CONST = 1536;
constexpr int PAR_RED = 1600;
constexpr int PAR_SINK = 2176;

struct Maps {
  CUtensorMap x, wq, k, v, wo, wg, wu, wd, wm, out;
};
struct Ptrs {
  const __nv_bfloat16 *x, *w_r, *c, *w_mod, *w_gate, *w_up, *w_down;
  __nv_bfloat16* out;
};

__device__ __align__(1024) uint8_t g_act[16 * 80 * UNIT];
__device__ __align__(128) uint32_t g_mod[NMOD];
__device__ __align__(128) uint32_t g_modp[2 * 2 * DM];
__device__ __align__(128) uint32_t g_ln1[SEQ * 4];
__device__ __align__(128) uint32_t g_cnt_h[16 * 32];
__device__ __align__(128) uint32_t g_cnt_o[128 * 32];
__device__ __align__(128) uint32_t g_xch[NMAIN * 8 * 256 * 4];
__device__ __align__(128) uint32_t g_stats[8 * SEQ * 4];
__device__ __align__(128) uint32_t g_cand[32];
__device__ __align__(128) uint32_t g_row[16 * 2 * DM];
__device__ __align__(128) uint32_t g_ypart[NMAIN * NFFN * 8];
__device__ uint32_t g_epoch;

__device__ __forceinline__ uint32_t fresh_lane() { uint32_t l; asm volatile("mov.u32 %0, %%laneid;" : "=r"(l)); return l; }
__device__ __forceinline__ uint32_t frag_offset(int warp) {
  const uint32_t l = fresh_lane();
  return ((warp & 3) * 16 + (l & 15)) * 128 + (((l >> 4) ^ (l & 7)) << 4);
}
__device__ __forceinline__ bool elect_one() {
  uint32_t p;
  asm volatile("{ .reg .pred q; elect.sync _|q, 0xffffffff; selp.u32 %0, 1, 0, q; }" : "=r"(p));
  return p;
}
__device__ __forceinline__ uint32_t smem_u32(const void* p) { return (uint32_t)__cvta_generic_to_shared(p); }
__device__ __forceinline__ void mbar_init(uint32_t bar, uint32_t cnt) {
  asm volatile("mbarrier.init.shared::cta.b64 [%0], %1;" ::"r"(bar), "r"(cnt) : "memory");
}
__device__ __forceinline__ void mbar_expect_tx(uint32_t bar, uint32_t bytes) {
  asm volatile("mbarrier.arrive.expect_tx.shared::cta.b64 _, [%0], %1;" ::"r"(bar), "r"(bytes) : "memory");
}
__device__ __forceinline__ void mbar_arrive(uint32_t bar) {
  asm volatile("mbarrier.arrive.shared::cta.b64 _, [%0];" ::"r"(bar) : "memory");
}
__device__ __forceinline__ void mbar_arrive_pred(uint32_t bar, bool p) {
  asm volatile("{ .reg .pred p; setp.ne.b32 p, %1, 0; @p mbarrier.arrive.shared::cta.b64 _, [%0]; }" ::"r"(bar), "r"((int)p) : "memory");
}
__device__ __forceinline__ void mbar_arrive_cl(uint32_t bar, uint32_t off, bool p = true) {
  asm volatile("{ .reg .pred p, q; .reg .b32 a; setp.ne.b32 q, %2, 0; setp.ne.and.b32 p, %0, 0, q; add.u32 a, %0, %1; @p mbarrier.arrive.shared::cluster.b64 _, [a]; }"
               ::"r"(bar), "r"(off), "r"((int)p) : "memory");
}
__device__ __forceinline__ uint32_t mapa(uint32_t addr, uint32_t cta) {
  uint32_t r; asm("mapa.shared::cluster.u32 %0, %1, %2;" : "=r"(r) : "r"(addr), "r"(cta)); return r;
}
__device__ __forceinline__ void cluster_arrive() { asm volatile("barrier.cluster.arrive.relaxed.aligned;" ::: "memory"); }
__device__ __forceinline__ void cluster_wait() { asm volatile("barrier.cluster.wait.aligned;" ::: "memory"); }
__device__ __forceinline__ void watchdog(uint32_t& n) {
}
__device__ __forceinline__ void mbar_wait(uint32_t bar, uint32_t parity) {
  asm volatile("{\n.reg .pred p;\nWAIT_%=:\nmbarrier.try_wait.parity.shared::cta.b64 p, [%0], %1;\n@!p bra WAIT_%=;\n}" ::"r"(bar), "r"(parity) : "memory");
}
__device__ __forceinline__ bool mbar_test(uint32_t bar, uint32_t parity) {
  uint32_t ok;
  asm volatile("{\n.reg .pred p;\nmbarrier.test_wait.parity.shared::cta.b64 p, [%1], %2;\nselp.u32 %0, 1, 0, p;\n}" : "=r"(ok) : "r"(bar), "r"(parity) : "memory");
  return ok;
}
__device__ __forceinline__ uint64_t l2_stream() {
  uint64_t f; asm("createpolicy.fractional.L2::evict_first.b64 %0, 1.0;" : "=l"(f)); return f;
}
__device__ __forceinline__ void tma2d(uint32_t dst, const CUtensorMap* m, int c0, int c1, uint32_t bar) {
  asm volatile("cp.async.bulk.tensor.2d.shared::cluster.global.mbarrier::complete_tx::bytes.L2::cache_hint [%0], [%1, {%3, %4}], [%2], %5;"
               ::"r"(dst), "l"(m), "r"(bar), "r"(c0), "r"(c1), "l"(l2_stream()) : "memory");
}
__device__ __forceinline__ void bulk_load(uint32_t dst, const void* src, uint32_t bytes, uint32_t bar) {
  asm volatile("cp.async.bulk.shared::cluster.global.mbarrier::complete_tx::bytes [%0], [%1], %2, [%3];" ::"r"(dst), "l"(src), "r"(bytes), "r"(bar) : "memory");
}
__device__ __forceinline__ void bulk_load_stream(uint32_t dst, const void* src, uint32_t bytes, uint32_t bar) {
  asm volatile("cp.async.bulk.shared::cluster.global.mbarrier::complete_tx::bytes.L2::cache_hint [%0], [%1], %2, [%3], %4;"
               ::"r"(dst), "l"(src), "r"(bytes), "r"(bar), "l"(l2_stream()) : "memory");
}
__device__ __forceinline__ void tma2d_store(const CUtensorMap* m, uint32_t src, int c0, int c1) {
  asm volatile("cp.async.bulk.tensor.2d.global.shared::cta.bulk_group [%0, {%2, %3}], [%1];" ::"l"(m), "r"(src), "r"(c0), "r"(c1) : "memory");
}
__device__ __forceinline__ void bulk_store(void* dst, uint32_t src, uint32_t bytes) {
  asm volatile("cp.async.bulk.global.shared::cta.bulk_group [%0], [%1], %2;" ::"l"(dst), "r"(src), "r"(bytes) : "memory");
}
__device__ __forceinline__ uint32_t unit_of(uint32_t table, uint32_t i) { return ((table >> (i * 4)) & 15) * UNIT; }
__device__ __forceinline__ void tma3d(uint32_t dst, const CUtensorMap* m, int c0, int c1, int c2, uint32_t bar) {
  asm volatile("cp.async.bulk.tensor.3d.shared::cluster.global.mbarrier::complete_tx::bytes.L2::cache_hint [%0], [%1, {%3, %4, %5}], [%2], %6;"
               ::"r"(dst), "l"(m), "r"(bar), "r"(c0), "r"(c1), "r"(c2), "l"(l2_stream()) : "memory");
}
template <bool STREAM>
__device__ __forceinline__ void tma3d_mc(uint32_t dst, const CUtensorMap* m, int c0, int c1, int c2, uint32_t bar) {
  if (STREAM)
    asm volatile("cp.async.bulk.tensor.3d.shared::cluster.global.mbarrier::complete_tx::bytes.multicast::cluster.L2::cache_hint [%0], [%1, {%3, %4, %5}], [%2], %6, %7;"
                 ::"r"(dst), "l"(m), "r"(bar), "r"(c0), "r"(c1), "r"(c2), "h"((uint16_t)3), "l"(l2_stream()) : "memory");
  else
    asm volatile("cp.async.bulk.tensor.3d.shared::cluster.global.mbarrier::complete_tx::bytes.multicast::cluster [%0], [%1, {%3, %4, %5}], [%2], %6;"
                 ::"r"(dst), "l"(m), "r"(bar), "r"(c0), "r"(c1), "r"(c2), "h"((uint16_t)3) : "memory");
}
__device__ __forceinline__ void prefetch_map(const CUtensorMap* m) {
  asm volatile("prefetch.tensormap [%0];" ::"l"(m) : "memory");
}
__device__ __forceinline__ void fence_async() { asm volatile("fence.proxy.async.global;" ::: "memory"); }
__device__ __forceinline__ void fence_async_smem() { asm volatile("fence.proxy.async.shared::cta;" ::: "memory"); }
__device__ __forceinline__ void bar_sync(int id, int n) { asm volatile("bar.sync %0, %1;" ::"r"(id), "r"(n) : "memory"); }
__device__ __forceinline__ void bar_arrive(int id, int n) { asm volatile("bar.arrive %0, %1;" ::"r"(id), "r"(n) : "memory"); }
__device__ __forceinline__ void wg_fence() { asm volatile("wgmma.fence.sync.aligned;" ::: "memory"); }
__device__ __forceinline__ void wg_commit() { asm volatile("wgmma.commit_group.sync.aligned;" ::: "memory"); }
template <int N> __device__ __forceinline__ void wg_wait() { asm volatile("wgmma.wait_group.sync.aligned %0;" ::"n"(N) : "memory"); }
__device__ __forceinline__ uint64_t make_desc(uint32_t addr, uint32_t lbo, uint32_t sbo) {
  return (uint64_t)((addr & 0x3FFFF) >> 4) | ((uint64_t)(lbo >> 4) << 16) | ((uint64_t)(sbo >> 4) << 32) | (1ull << 62);
}
__device__ __forceinline__ uint32_t ld_relaxed(const uint32_t* p) {
  uint32_t v; asm volatile("ld.relaxed.gpu.global.u32 %0, [%1];" : "=r"(v) : "l"(p) : "memory"); return v;
}
__device__ __forceinline__ uint32_t ld_acquire(const uint32_t* p) {
  uint32_t v; asm volatile("ld.acquire.gpu.global.u32 %0, [%1];" : "=r"(v) : "l"(p) : "memory"); return v;
}
__device__ __forceinline__ uint4 ld_relaxed4(const uint32_t* p) {
  uint4 v; asm volatile("ld.relaxed.gpu.global.v4.u32 {%0,%1,%2,%3}, [%4];" : "=r"(v.x), "=r"(v.y), "=r"(v.z), "=r"(v.w) : "l"(p) : "memory"); return v;
}
__device__ __forceinline__ uint2 ld_relaxed2(const uint32_t* p) {
  uint2 v; asm volatile("ld.relaxed.gpu.global.v2.u32 {%0,%1}, [%2];" : "=r"(v.x), "=r"(v.y) : "l"(p) : "memory"); return v;
}
__device__ __forceinline__ void st_relaxed(uint32_t* p, uint32_t v) {
  asm volatile("st.relaxed.gpu.global.u32 [%0], %1;" ::"l"(p), "r"(v) : "memory");
}
__device__ __forceinline__ void st_relaxed2(uint32_t* p, uint32_t a, uint32_t b) {
  asm volatile("st.relaxed.gpu.global.v2.u32 [%0], {%1,%2};" ::"l"(p), "r"(a), "r"(b) : "memory");
}
__device__ __forceinline__ void st_relaxed4(uint32_t* p, uint32_t a, uint32_t b, uint32_t c, uint32_t d) {
  asm volatile("st.relaxed.gpu.global.v4.u32 [%0], {%1,%2,%3,%4};" ::"l"(p), "r"(a), "r"(b), "r"(c), "r"(d) : "memory");
}
__device__ __forceinline__ void st_b128(uint32_t* p, uint32_t a, uint32_t b, uint32_t c, uint32_t d) {
  asm volatile("{ .reg .b64 u, v; .reg .b128 w; mov.b64 u, {%1, %2}; mov.b64 v, {%3, %4}; mov.b128 w, {u, v}; st.relaxed.gpu.global.b128 [%0], w; }"
               ::"l"(p), "r"(a), "r"(b), "r"(c), "r"(d) : "memory");
}
__device__ __forceinline__ uint4 ld_b128(const uint32_t* p) {
  uint4 r;
  asm volatile("{ .reg .b64 u, v; .reg .b128 w; ld.relaxed.gpu.global.b128 w, [%4]; mov.b128 {u, v}, w; mov.b64 {%0, %1}, u; mov.b64 {%2, %3}, v; }"
               : "=r"(r.x), "=r"(r.y), "=r"(r.z), "=r"(r.w) : "l"(p) : "memory");
  return r;
}
__device__ __forceinline__ void st_pairs(uint32_t* p, uint32_t a, uint32_t b, uint32_t tag) {
  asm volatile("{ .reg .b64 u, v; mov.b64 u, {%1, %3}; mov.b64 v, {%2, %3}; st.relaxed.gpu.global.v2.b64 [%0], {u, v}; }"
               ::"l"(p), "r"(a), "r"(b), "r"(tag) : "memory");
}
__device__ __forceinline__ uint4 ld_pairs(const uint32_t* p) {
  uint4 v;
  asm volatile("{ .reg .b64 u, v; ld.relaxed.gpu.global.v2.b64 {u, v}, [%4]; mov.b64 {%0, %1}, u; mov.b64 {%2, %3}, v; }"
               : "=r"(v.x), "=r"(v.y), "=r"(v.z), "=r"(v.w) : "l"(p) : "memory");
  return v;
}
__device__ __forceinline__ uint2 ld_pair(const uint32_t* p) {
  uint2 v;
  asm volatile("{ .reg .b64 u; ld.relaxed.gpu.global.b64 u, [%2]; mov.b64 {%0, %1}, u; }" : "=r"(v.x), "=r"(v.y) : "l"(p) : "memory");
  return v;
}
__device__ __forceinline__ void red_release(uint32_t* p, uint32_t v) {
  asm volatile("red.release.gpu.global.add.u32 [%0], %1;" ::"l"(p), "r"(v) : "memory");
}
__device__ __forceinline__ uint32_t ldg_nc1(const void* p) {
  uint32_t v;
  asm volatile("ld.global.nc.u32 %0, [%1];" : "=r"(v) : "l"(p));
  return v;
}
__device__ __forceinline__ uint4 ldg_nc4(const void* p) {
  uint4 v; asm volatile("ld.global.nc.L1::no_allocate.v4.u32 {%0,%1,%2,%3}, [%4];" : "=r"(v.x), "=r"(v.y), "=r"(v.z), "=r"(v.w) : "l"(p)); return v;
}
__device__ __forceinline__ uint4 ldg_stream4(const void* p) {
  uint4 v;
  asm volatile("ld.global.nc.L1::no_allocate.L2::cache_hint.v4.u32 {%0,%1,%2,%3}, [%4], %5;" : "=r"(v.x), "=r"(v.y), "=r"(v.z), "=r"(v.w) : "l"(p), "l"(l2_stream()));
  return v;
}
__device__ __forceinline__ void stg4(void* p, uint4 v) {
  asm volatile("st.global.v4.u32 [%0], {%1,%2,%3,%4};" ::"l"(p), "r"(v.x), "r"(v.y), "r"(v.z), "r"(v.w) : "memory");
}
__device__ __forceinline__ void wait_counter(const uint32_t* p, uint32_t target) {
  uint32_t n = 0;
  while (__any_sync(0xffffffffu, (int)(ld_acquire(p) - target) < 0)) { watchdog(n); }
}
__device__ __forceinline__ uint32_t tagf(float v, uint32_t tag) { return (__float_as_uint(v) & ~3u) | tag; }
__device__ __forceinline__ bool tag_ok(uint4 v, uint32_t tag) { return (((v.x ^ tag) | (v.y ^ tag) | (v.z ^ tag) | (v.w ^ tag)) & 3u) == 0; }
__device__ __forceinline__ float untag_sum(uint32_t a, uint32_t b) { return __uint_as_float(a & ~3u) + __uint_as_float(b & ~3u); }
__device__ __forceinline__ uint4 poll4(const uint32_t* p, uint32_t tag) {
  uint4 v = ld_relaxed4(p);
  uint32_t n = 0;
  while (!__all_sync(0xffffffffu, tag_ok(v, tag))) { v = ld_relaxed4(p); watchdog(n); }
  return v;
}
__device__ __forceinline__ float bf_lo(uint32_t v) { return __uint_as_float(v << 16); }
__device__ __forceinline__ float bf_hi(uint32_t v) { return __uint_as_float(v & 0xffff0000u); }
__device__ __forceinline__ uint32_t pack_bf(float lo, float hi) {
  uint32_t r; asm("cvt.rn.bf16x2.f32 %0, %1, %2;" : "=r"(r) : "f"(hi), "f"(lo)); return r;
}
__device__ __forceinline__ float rbf(float v) { return __uint_as_float(pack_bf(0.f, v) & 0xffff0000u); }
__device__ __forceinline__ uint32_t hmul2(uint32_t a, uint32_t b) {
  uint32_t r; asm("mul.rn.bf16x2 %0, %1, %2;" : "=r"(r) : "r"(a), "r"(b)); return r;
}
__device__ __forceinline__ uint32_t hadd2(uint32_t a, uint32_t b) {
  uint32_t r; asm("add.rn.bf16x2 %0, %1, %2;" : "=r"(r) : "r"(a), "r"(b)); return r;
}
__device__ __forceinline__ uint32_t hsub2(uint32_t a, uint32_t b) {
  uint32_t r; asm("sub.rn.bf16x2 %0, %1, %2;" : "=r"(r) : "r"(a), "r"(b)); return r;
}
__device__ __forceinline__ uint32_t hmax2(uint32_t a, uint32_t b) {
  uint32_t r; asm("max.bf16x2 %0, %1, %2;" : "=r"(r) : "r"(a), "r"(b)); return r;
}
__device__ __forceinline__ float rcp(float x) { float r; asm("rcp.approx.ftz.f32 %0, %1;" : "=f"(r) : "f"(x)); return r; }
__device__ __forceinline__ float ex2(float x) { float r; asm("ex2.approx.ftz.f32 %0, %1;" : "=f"(r) : "f"(x)); return r; }
__device__ __forceinline__ void stmatrix4(uint32_t addr, uint32_t a, uint32_t b, uint32_t c, uint32_t d) {
  asm volatile("stmatrix.sync.aligned.m8n8.x4.shared.b16 [%0], {%1,%2,%3,%4};" ::"r"(addr), "r"(a), "r"(b), "r"(c), "r"(d) : "memory");
}
__device__ __forceinline__ void ldmatrix4(uint32_t addr, uint32_t& a, uint32_t& b, uint32_t& c, uint32_t& d) {
  asm volatile("ldmatrix.sync.aligned.m8n8.x4.shared.b16 {%0,%1,%2,%3}, [%4];" : "=r"(a), "=r"(b), "=r"(c), "=r"(d) : "r"(addr) : "memory");
}
__device__ __forceinline__ void ldmatrix4t(uint32_t addr, uint32_t& a, uint32_t& b, uint32_t& c, uint32_t& d) {
  asm volatile("ldmatrix.sync.aligned.m8n8.x4.trans.shared.b16 {%0,%1,%2,%3}, [%4];" : "=r"(a), "=r"(b), "=r"(c), "=r"(d) : "r"(addr) : "memory");
}
__device__ __forceinline__ void mma16816(float (&d)[4], uint32_t a0, uint32_t a1, uint32_t a2, uint32_t a3, uint32_t b0, uint32_t b1) {
  asm volatile("mma.sync.aligned.m16n8k16.row.col.f32.bf16.bf16.f32 {%0,%1,%2,%3}, {%4,%5,%6,%7}, {%8,%9}, {%0,%1,%2,%3};"
               : "+f"(d[0]), "+f"(d[1]), "+f"(d[2]), "+f"(d[3]) : "r"(a0), "r"(a1), "r"(a2), "r"(a3), "r"(b0), "r"(b1));
}
__device__ __forceinline__ void sts1(uint32_t a, uint32_t v) { asm volatile("st.shared.u32 [%0], %1;" ::"r"(a), "r"(v) : "memory"); }
__device__ __forceinline__ uint4 lds4(uint32_t a) {
  uint4 v; asm volatile("ld.shared.v4.u32 {%0,%1,%2,%3}, [%4];" : "=r"(v.x), "=r"(v.y), "=r"(v.z), "=r"(v.w) : "r"(a) : "memory"); return v;
}
__device__ __forceinline__ uint2 lds2(uint32_t a) {
  uint2 v; asm volatile("ld.shared.v2.u32 {%0,%1}, [%2];" : "=r"(v.x), "=r"(v.y) : "r"(a) : "memory"); return v;
}
__device__ __forceinline__ uint32_t lds1(uint32_t a) {
  uint32_t v; asm volatile("ld.shared.u32 %0, [%1];" : "=r"(v) : "r"(a) : "memory"); return v;
}
__device__ __forceinline__ void sts2(uint32_t a, uint32_t x, uint32_t y) { asm volatile("st.shared.v2.u32 [%0], {%1,%2};" ::"r"(a), "r"(x), "r"(y) : "memory"); }
__device__ __forceinline__ void sts4(uint32_t a, uint4 v) {
  asm volatile("st.shared.v4.u32 [%0], {%1,%2,%3,%4};" ::"r"(a), "r"(v.x), "r"(v.y), "r"(v.z), "r"(v.w) : "memory");
}
__device__ __forceinline__ float silu_f(float v) { return __fdividef(v, 1.f + __expf(-v)); }
__device__ __forceinline__ uint32_t hfma2(uint32_t a, uint32_t b, uint32_t c) {
  uint32_t r; asm("fma.rn.bf16x2 %0, %1, %2, %3;" : "=r"(r) : "r"(a), "r"(b), "r"(c)); return r;
}
__device__ __forceinline__ void split_inv(float sd, uint32_t& ih, uint32_t& il) {
  const float inv = rcp(sd);
  ih = pack_bf(inv, inv);
  const float lo = inv - bf_lo(ih);
  il = pack_bf(lo, lo);
}
__device__ __forceinline__ uint32_t ln_norm(uint32_t x, uint32_t mean2, uint32_t ih, uint32_t il) {
  const uint32_t d = hsub2(x, mean2);
  return hfma2(d, ih, hmul2(d, il));
}
__device__ __forceinline__ uint32_t modul(uint32_t n, uint32_t c1, uint32_t sh) { return hadd2(hmul2(n, c1), sh); }
__device__ __forceinline__ uint32_t ln_mod(uint32_t x, uint32_t mean2, uint32_t ih, uint32_t il, uint32_t c1, uint32_t sh) {
  return modul(ln_norm(x, mean2, ih, il), c1, sh);
}

#define R8(a, i) "+f"(a[i]), "+f"(a[i + 1]), "+f"(a[i + 2]), "+f"(a[i + 3]), "+f"(a[i + 4]), "+f"(a[i + 5]), "+f"(a[i + 6]), "+f"(a[i + 7])
#define D64 "{%0,%1,%2,%3,%4,%5,%6,%7,%8,%9,%10,%11,%12,%13,%14,%15,%16,%17,%18,%19,%20,%21,%22,%23,%24,%25,%26,%27,%28,%29,%30,%31," \
            "%32,%33,%34,%35,%36,%37,%38,%39,%40,%41,%42,%43,%44,%45,%46,%47,%48,%49,%50,%51,%52,%53,%54,%55,%56,%57,%58,%59,%60,%61,%62,%63}"
template <int TB>
__device__ __forceinline__ void mma_ss(float (&d)[64], uint64_t da, uint64_t db, int sc) {
  asm volatile("{\n.reg .pred p;\nsetp.ne.b32 p, %66, 0;\n"
               "wgmma.mma_async.sync.aligned.m64n128k16.f32.bf16.bf16 " D64 ", %64, %65, p, 1, 1, 0, %67;\n}"
               : R8(d, 0), R8(d, 8), R8(d, 16), R8(d, 24), R8(d, 32), R8(d, 40), R8(d, 48), R8(d, 56)
               : "l"(da), "l"(db), "r"(sc), "n"(TB));
}
template <int TB>
__device__ __forceinline__ void mma_rs(float (&d)[64], uint32_t a0, uint32_t a1, uint32_t a2, uint32_t a3, uint64_t db, int sc) {
  asm volatile("{\n.reg .pred p;\nsetp.ne.b32 p, %69, 0;\n"
               "wgmma.mma_async.sync.aligned.m64n128k16.f32.bf16.bf16 " D64 ", {%64,%65,%66,%67}, %68, p, 1, 1, %70;\n}"
               : R8(d, 0), R8(d, 8), R8(d, 16), R8(d, 24), R8(d, 32), R8(d, 40), R8(d, 48), R8(d, 56)
               : "r"(a0), "r"(a1), "r"(a2), "r"(a3), "l"(db), "r"(sc), "n"(TB));
}
#define D128 "{%0,%1,%2,%3,%4,%5,%6,%7,%8,%9,%10,%11,%12,%13,%14,%15,%16,%17,%18,%19,%20,%21,%22,%23,%24,%25,%26,%27,%28,%29,%30,%31," \
             "%32,%33,%34,%35,%36,%37,%38,%39,%40,%41,%42,%43,%44,%45,%46,%47,%48,%49,%50,%51,%52,%53,%54,%55,%56,%57,%58,%59,%60,%61,%62,%63," \
             "%64,%65,%66,%67,%68,%69,%70,%71,%72,%73,%74,%75,%76,%77,%78,%79,%80,%81,%82,%83,%84,%85,%86,%87,%88,%89,%90,%91,%92,%93,%94,%95," \
             "%96,%97,%98,%99,%100,%101,%102,%103,%104,%105,%106,%107,%108,%109,%110,%111,%112,%113,%114,%115,%116,%117,%118,%119,%120,%121,%122,%123,%124,%125,%126,%127}"
#define R128(d, e) R8(d, 0), R8(d, 8), R8(d, 16), R8(d, 24), R8(d, 32), R8(d, 40), R8(d, 48), R8(d, 56), \
                   R8(e, 0), R8(e, 8), R8(e, 16), R8(e, 24), R8(e, 32), R8(e, 40), R8(e, 48), R8(e, 56)
__device__ __forceinline__ void mma256_ss(float (&d)[64], float (&e)[64], uint64_t da, uint64_t db, int sc) {
  asm volatile("{\n.reg .pred p;\nsetp.ne.b32 p, %130, 0;\n"
               "wgmma.mma_async.sync.aligned.m64n256k16.f32.bf16.bf16 " D128 ", %128, %129, p, 1, 1, 0, 1;\n}"
               : R128(d, e) : "l"(da), "l"(db), "r"(sc));
}
__device__ __forceinline__ void mma256_rs(float (&d)[64], float (&e)[64], uint32_t a0, uint32_t a1, uint32_t a2, uint32_t a3, uint64_t db) {
  asm volatile("{\n.reg .pred p;\nsetp.ne.b32 p, 1, 0;\n"
               "wgmma.mma_async.sync.aligned.m64n256k16.f32.bf16.bf16 " D128 ", {%128,%129,%130,%131}, %132, p, 1, 1, 1;\n}"
               : R128(d, e) : "r"(a0), "r"(a1), "r"(a2), "r"(a3), "l"(db));
}
template <int N> __device__ __forceinline__ void keep(float (&a)[N]) {
#pragma unroll
  for (int i = 0; i < N; i++) asm volatile("" : "+f"(a[i])::"memory");
}
template <int N> __device__ __forceinline__ void keep(uint32_t (&a)[N]) {
#pragma unroll
  for (int i = 0; i < N; i++) asm volatile("" : "+r"(a[i])::"memory");
}

#define STAMP(idx) do {} while (0)
#define PROF(grp, cond, idx) do {} while (0)

constexpr float SCL2 = 1.4426950408889634f * 0.08838834764831845f;

__device__ __forceinline__ void pack_p(const float (&s)[64], uint32_t (&p)[32]) {
#pragma unroll
  for (int i = 0; i < 32; i++) p[i] = pack_bf(s[2 * i], s[2 * i + 1]);
}

__device__ __forceinline__ void issue_qk(float (&s)[64], uint32_t q0, uint32_t q1, uint32_t kslot) {
  const uint64_t db = make_desc(kslot, 16, 1024), da0 = make_desc(q0, 16, 1024), da1 = make_desc(q1, 16, 1024);
#pragma unroll
  for (int kk = 0; kk < 8; kk++) mma_ss<0>(s, (kk < 4 ? da0 : da1) + (kk & 3) * 2, db + (kk >> 2) * 1024 + (kk & 3) * 2, kk != 0);
}
__device__ __forceinline__ void issue_pv(float (&o)[64], uint32_t (&p)[32], uint32_t vslot, int acc) {
  uint64_t db = make_desc(vslot, 16384, 1024);
#pragma unroll
  for (int kk = 0; kk < 8; kk++)
    mma_rs<1>(o, p[4 * kk], p[4 * kk + 1], p[4 * kk + 2], p[4 * kk + 3], db + kk * 128, kk == 0 ? acc : 1);
}

template <int H>
__device__ __forceinline__ void store_chunk(const float (&a)[64], uint32_t addr) {
#pragma unroll
  for (int i = 8 * H; i < 8 * H + 8; i += 2)
    stmatrix4(addr ^ ((i & 7) << 4), pack_bf(a[4 * i], a[4 * i + 1]), pack_bf(a[4 * i + 2], a[4 * i + 3]),
              pack_bf(a[4 * i + 4], a[4 * i + 5]), pack_bf(a[4 * i + 6], a[4 * i + 7]));
}
template <int H>
__device__ __forceinline__ void store_chunk(const float (&a)[64], float i0, float i1, uint32_t addr) {
#pragma unroll
  for (int i = 8 * H; i < 8 * H + 8; i += 2)
    stmatrix4(addr ^ ((i & 7) << 4), pack_bf(a[4 * i] * i0, a[4 * i + 1] * i0), pack_bf(a[4 * i + 2] * i1, a[4 * i + 3] * i1),
              pack_bf(a[4 * i + 4] * i0, a[4 * i + 5] * i0), pack_bf(a[4 * i + 6] * i1, a[4 * i + 7] * i1));
}
__device__ __forceinline__ float inv_quad_sum(float l) {
  l += __shfl_xor_sync(0xffffffffu, l, 1);
  l += __shfl_xor_sync(0xffffffffu, l, 2);
  return rcp(l);
}

__device__ __forceinline__ void ln_scalars(float mean, float var, float& mb, float& sd) {
  mb = rbf(mean);
  float r; asm("sqrt.approx.ftz.f32 %0, %1;" : "=f"(r) : "f"(rbf(rbf(var) + 1e-5f)));
  sd = rbf(r);
}

__global__ void __cluster_dims__(2, 1, 1) __launch_bounds__(384, 1) fused_kernel(const __grid_constant__ Maps maps, const Ptrs P) {
  extern __shared__ __align__(1024) uint8_t smem_raw[];
  const uint32_t base = smem_u32(smem_raw);
  const int tid = threadIdx.x, lane = tid & 31;
  const int warp = __shfl_sync(0xffffffffu, tid >> 5, 0);
  const int b = blockIdx.x;
  PROF(31, tid == 0, 0);

  if (b >= NMAIN) {
    float* sc = reinterpret_cast<float*>(smem_raw);
    float* red = sc + DM;
    for (int k = tid; k < DM; k += 384) sc[k] = rbf(silu_f(__bfloat162float(P.c[k])));
    __syncthreads();
    if (tid < 256) {
      const int col = 2048 + (b - NMAIN) * 1024 + (tid & 127) * 8, r0 = (tid >> 7) * 512;
      float acc[8];
#pragma unroll
      for (int e = 0; e < 8; e++) acc[e] = 0.f;
#pragma unroll 1
      for (int r = r0; r < r0 + 512; r += HU) {
        uint4 w[HU];
#pragma unroll
        for (int u = 0; u < HU; u++) w[u] = ldg_stream4(P.w_mod + (size_t)(r + u) * NMOD + col);
#pragma unroll
        for (int u = 0; u < HU; u++) {
          float s = sc[r + u];
          acc[0] += s * bf_lo(w[u].x); acc[1] += s * bf_hi(w[u].x); acc[2] += s * bf_lo(w[u].y); acc[3] += s * bf_hi(w[u].y);
          acc[4] += s * bf_lo(w[u].z); acc[5] += s * bf_hi(w[u].z); acc[6] += s * bf_lo(w[u].w); acc[7] += s * bf_hi(w[u].w);
        }
      }
      if (tid >= 128) {
#pragma unroll
        for (int e = 0; e < 8; e++) red[(tid & 127) * 8 + e] = acc[e];
      }
      const uint32_t tag = ld_relaxed(&g_epoch) % 3 + 1;
      bar_sync(1, 256);
      if (tid < 128) {
        uint32_t o[8];
#pragma unroll
        for (int e = 0; e < 8; e++) o[e] = __float_as_uint(rbf(acc[e] + red[tid * 8 + e])) | tag;
        st_relaxed4(g_mod + col, o[0], o[1], o[2], o[3]);
        st_relaxed4(g_mod + col + 4, o[4], o[5], o[6], o[7]);
        const uint4 wr = ldg_nc4(P.w_r + tid * 8);
        const uint32_t wv[4] = {wr.x, wr.y, wr.z, wr.w};
        float dsum = 0.f;
#pragma unroll
        for (int e = 0; e < 8; e++) {
          const float m = bf_hi(o[e]);
          dsum += (b == NMAIN + 2 ? rbf(1.f + m) : m) * ((e & 1) ? bf_hi(wv[e >> 1]) : bf_lo(wv[e >> 1]));
        }
#pragma unroll
        for (int k = 16; k > 0; k >>= 1) dsum += __shfl_xor_sync(0xffffffffu, dsum, k);
        if (lane == 0) st_relaxed(g_mod + (b - NMAIN) * 4 + warp, tagf(dsum, tag));
      }
    }
    PROF(2, tid == 0, 1);
    return;
  }

  const int rank = b & 1;
  const int rb = ((b >> 4) << 1) | rank, cj = (b >> 1) & 7;
  const uint32_t bfull = base + OFF_BAR, bempty = bfull + NSLOT * 8;
  const uint32_t gfull = bempty + NSLOT * 8, gempty = gfull + 32;
  const uint32_t bar_ofull = gempty + 32;
  const uint32_t bar_ofree = bar_ofull + 32;
  const uint32_t bar_par = bar_ofree + 32;
  const uint32_t bar_mod = bar_par + 8;
  const uint32_t bar_pread = bar_mod + 8;
  const uint32_t bar_xres = bar_pread + 8;
  const uint32_t bar_ring = bar_xres + 8;
  const uint32_t bar_box = bar_ring + 24;
  const uint32_t bar_go = bar_box + 96;
  const uint32_t bar_go2 = bar_go + 16;
  const uint32_t bar_cnt = bar_go + 24;
  const uint32_t xfull = bar_go + 40, xempty = xfull + 32;
  const uint32_t bar_hw = xempty + 32, bar_hx = bar_hw + 8;
  const uint32_t bar_hpub = bar_hx + 16;
  const uint32_t bar_win = bar_hpub + 16;
  const uint32_t bar_rx = bar_win + 8;
  const uint32_t bar_sel = bar_rx + 8;
  const uint32_t bar_gate = bar_sel + 8;
  const uint32_t bar_rel = bar_gate + 8;
  const uint32_t bar_od = bar_rel + 8;
  const uint32_t bar_res = bar_go + 8;
  const uint32_t stage = base + OFF_STAGE, par = base + OFF_PAR;

  if (warp == 8 && elect_one()) {
    for (int s = 0; s < NSLOT; s++) { mbar_init(bfull + s * 8, 1); mbar_init(bempty + s * 8, 16); }
    for (int s = 0; s < 4; s++) { mbar_init(gfull + s * 8, 1); mbar_init(gempty + s * 8, 16); mbar_init(xfull + s * 8, 1); mbar_init(xempty + s * 8, 8); mbar_init(bar_ofree + s * 8, 1); mbar_init(bar_ofull + s * 8, 128); }
    mbar_init(bar_par, 64); mbar_init(bar_mod, 256); mbar_init(bar_pread, 2); mbar_init(bar_xres, 1);
    mbar_init(bar_ring, 8); mbar_init(bar_ring + 8, 8); mbar_init(bar_ring + 16, 8);
    mbar_init(bar_go, 1); mbar_init(bar_go2, 1); mbar_init(bar_cnt, 1); mbar_init(bar_cnt + 8, 1); mbar_init(bar_hpub, 8); mbar_init(bar_hpub + 8, 8); mbar_init(bar_res, 1); mbar_init(bar_win, 1); mbar_init(bar_rx, 1); mbar_init(bar_sel, 64); mbar_init(bar_gate, 8); mbar_init(bar_rel, 8); mbar_init(bar_od, 1);
    for (int s = 0; s < 12; s++) mbar_init(bar_box + s * 8, 1);
    asm volatile("fence.mbarrier_init.release.cluster;" ::: "memory");
    prefetch_map(&maps.x); prefetch_map(&maps.wq); prefetch_map(&maps.k); prefetch_map(&maps.v);
  }
  if (warp == 9 && elect_one()) {
    mbar_init(bar_hw, 1); mbar_init(bar_hx, 1); mbar_init(bar_hx + 8, 1);
    asm volatile("fence.mbarrier_init.release.cluster;" ::: "memory");
    mbar_expect_tx(bar_hw, 32768);
    mbar_expect_tx(bar_hx, 16384);
    mbar_expect_tx(bar_hx + 8, 16384);
    const __nv_bfloat16* xs = P.x + (size_t)(rb * 128 + cj * 16) * DM;
    bulk_load(base + 2 * GST_BYTES, xs, 16384, bar_hx);
    tma2d(stage, &maps.wm, (b >> 1) * 32, rank * 512, bar_hw);
    tma2d(stage + 16384, &maps.wm, (b >> 1) * 32, rank * 512 + 256, bar_hw);
    bulk_load(base + 3 * GST_BYTES, xs + 8 * DM, 16384, bar_hx + 8);
  }
  cluster_arrive();

  if (warp >= 8) {
    asm volatile("setmaxnreg.dec.sync.aligned.u32 40;");
    if (warp < 10) bar_arrive(1, 320);
    const uint32_t epoch = ld_relaxed(&g_epoch);
    cluster_wait();
    if (warp == 8) {
      const int kvrow = (cj >> 1) * SK + (SK - WIN);
      int wch = cj * 8 + rank * 2;
#pragma unroll 1
      for (int ps = 0; ps < 3; ps++) {
        const CUtensorMap* mw = ps == 2 ? &maps.wo : &maps.wq;
        const uint32_t xt = ps == 1 ? XT1 : XT2, wt = ps == 0 ? WT0 : (ps == 1 ? WT1 : WT2);
        const int nst = ps == 2 ? 32 : 16;
#pragma unroll 1
        for (int i = 0; i < nst; i++) {
          const uint32_t bf = gfull + (i & 3) * 8;
          const int kt = ps == 2 ? (((cj & 1) * 4 + ((i >> 1) & 3)) * 4 + (i >> 3)) * 2 + (i & 1) : (i + (ps ? 0 : b & 14)) & 15;
          const uint32_t wd = base + unit_of(wt, i & 3) + rank * UNIT, xd = base + unit_of(xt, i & 3);
          const uint8_t* xs = g_act + (uint32_t)(rb * 80 + (ps - 1) * 16 + kt) * UNIT;
          if (ps == 0 && i == HD) mbar_wait(bar_mod, 0);
          const bool xfirst = ps && i < 2;
          if (ps == 2 && i == 0) mbar_wait(bar_ofree + 24, 0);
          if (i == 0) fence_async();
          mbar_wait(gempty + (i & 3) * 8, ((i >> 2) & 1) ^ 1);
          if (elect_one()) {
            mbar_expect_tx(bf, ps ? GST_BYTES : 2 * UNIT);
            if (xfirst) bulk_load_stream(xd, xs, UNIT, bf);
          }
          if (ps && i < 4) mbar_wait(bempty + i * 8, 1);
          if (elect_one()) tma3d_mc<true>(wd, mw, 0, (i == 31 ? kt ^ (rank * 32) : kt) * 64, i == 31 ? cj * 2 : wch, bf);
          if (ps) {
            if (i == 16 || i == 24) { mbar_wait(bar_cnt + i - 16, 0); fence_async(); }
            if (i == RES0) mbar_wait(bar_res, 0);
            if (i == 2) mbar_wait(bar_ofree + (ps - 1) * 16, 0);
            if (elect_one()) {
              if (i == 31) bulk_load(xd, xs, UNIT, bf); else if (!xfirst) bulk_load_stream(xd, xs, UNIT, bf);
              mbar_arrive_pred(bar_go, i == GOST - 1);
              mbar_arrive_pred(bar_od, i == ODS);
              if (i == RES0) mbar_expect_tx(bar_xres, 32768);
              if (i == RES0 || i == RES1) tma2d(base + OFF_RES + (i == RES1) * UNIT, &maps.x, cj * 128 + (i == RES1) * 64, rb * 128, bar_xres);
            }
          }
        }
        if (ps == 2) break;
        wch = ps ? ((wch >> 3) ^ rank) * 2 : wch + 4;
#pragma unroll 1
        for (int u = 0; u < 16; u++) {
          const bool isk = (u == 0) || ((u & 1) && u < 15);
          const int blk = (isk ? (u + 1) >> 1 : (u == 15 ? 7 : (u >> 1) - 1)) & 3;
          const uint32_t sl = base + unit_of(ps ? AT1 : AT0, u & 3) + rank * UNIT, bf = bfull + (u & 3) * 8;
          if (u < 4) mbar_wait(gempty + ((u + 1) >> 1) * 8, 1);
          mbar_wait(bempty + (u & 3) * 8, ((u >> 2) & 1) ^ 1);
          if (elect_one()) {
            mbar_arrive_pred(bar_go2, ps && u == PG0);
            mbar_expect_tx(bf, SLOT_BYTES);
            tma3d_mc<false>(sl, isk ? &maps.k : &maps.v, 0, kvrow + blk * 128, rank, bf);
          }
        }
      }
      if (elect_one()) mbar_expect_tx(bar_rx, UNIT);
      mbar_wait(bar_rel, 0);
      if (elect_one()) {
        bulk_load_stream(base + UNIT, g_act + (uint32_t)(rb * 80 + 16 + 63 - (cj & 1) * 32) * UNIT, UNIT, bar_rx);
      }
      if (b < NFFN) {
#pragma unroll 1
        for (int u = 0; u < 12; u++) {
          const uint32_t dst = base + unit_of(u < 4 ? FT_G : (u < 8 ? FT_U : FT_D), u & 3);
          if (elect_one()) mbar_expect_tx(bar_box + u * 8, UNIT);
          if (u == FB0 || u == 2 || u == FB2) mbar_wait(bar_ring + (u == FB2 ? 16 : (u + 6) & 8), 0);
          if (u >= FPACE) mbar_wait(bar_box + (u - FPACE) * 8, 0);
          if (elect_one()) {
            if (u < 8) tma2d(dst, u < 4 ? &maps.wg : &maps.wu, b * 32, (u & 3) * 256, bar_box + u * 8);
            else tma3d(dst, &maps.wd, 0, b * 32, (u - 8) * 4, bar_box + u * 8);
          }
        }
      }
    } else if (warp == 9) {
      const uint32_t target = 8 * (epoch + 1);
      uint32_t hmask = 0;
#pragma unroll 1
      for (int i = 0; i < 16; i++) {
        if (i == HDX) mbar_wait(bar_mod, 0);
        const uint32_t need = i == 15 ? 0xffffu : 1u << ((2 * cj + i) & 15);
        if (i >= NRS && (hmask & need) != need) {
          uint32_t n = 0;
          do { hmask = __ballot_sync(0xffffffffu, ld_acquire(&g_cnt_h[rb * 32 + (lane & 15)]) == epoch + 1); watchdog(n); } while ((hmask & need) != need);
          PROF(1, lane == 0 && i == NRS, 26);
          fence_async();
        }
        mbar_wait(xempty + (i & 3) * 8, ((i >> 2) & 1) ^ 1);
        if (elect_one()) {
          mbar_expect_tx(xfull + (i & 3) * 8, UNIT);
          if (i < NRS) tma2d(base + (i & 3) * GST_BYTES, &maps.x, ((2 * cj + i) & 15) * 64, rb * 128, xfull + (i & 3) * 8);
          else bulk_load_stream(base + (i & 3) * GST_BYTES, g_act + (uint32_t)(rb * 80 + ((2 * cj + i) & 15)) * UNIT, UNIT, xfull + (i & 3) * 8);
        }
      }
      prefetch_map(&maps.wo);
#pragma unroll 1
      for (int t = 0; t < 4; t++) {
        if (t & 1) mbar_wait(bar_od, t >> 1);
#pragma unroll 1
        for (int p = 0; p < 32768 / OPS; p++) {
          const uint32_t w = p / (16384 / OPS), c = (p / (8192 / OPS)) & 1, off = w * 8192 + (p % (8192 / OPS)) * OPS;
          mbar_wait(bar_ofull + (t & 1) * 16 + w * 8, t >> 1);
          if (elect_one()) {
            bulk_store(g_act + (uint32_t)(rb * 80 + 16 + (cj * 4 + t) * 2 + c) * UNIT + off, base + unit_of(QT, 2 * t + c) + off, OPS);
            asm volatile("cp.async.bulk.commit_group;" ::: "memory");
            asm volatile("cp.async.bulk.wait_group.read %0;" ::"n"(OFL) : "memory");
          }
        }
        if (elect_one()) {
          asm volatile("cp.async.bulk.wait_group.read 0;" ::: "memory");
          mbar_arrive(t < 3 ? bar_ofree + t * 8 : bar_res);
          asm volatile("cp.async.bulk.wait_group 0;" ::: "memory");
          fence_async();
          red_release(&g_cnt_o[((rb * 4 + t) * 2 + (cj >> 2)) * 32], 2);
        }
        if (t) {
          wait_counter(&g_cnt_o[(rb * 8 + 2 * t + (cj & 1)) * 32], target);
          if (t & 1) wait_counter(&g_cnt_o[(rb * 8 + (t == 1 ? cj & 1 : 7 - (cj & 1))) * 32], target);
          if (elect_one()) mbar_arrive(t == 1 ? bar_ofree + 24 : bar_cnt + t * 8 - 16);
        }
      }
      PROF(2, lane == 0, 27);
      const uint32_t tag = epoch % 3 + 1;
      const uint32_t* inbox = g_cand + (lane & 15);
      mbar_wait(bar_ring + 16, 0);
      uint32_t c0 = ld_relaxed(inbox), n = 0;
#define CAND_STEP(cv)                                                                                        \
      {                                                                                                      \
        const bool valid = (cv & 3u) == tag, all = __all_sync(0xffffffffu, valid);                           \
        const uint32_t best = __reduce_max_sync(0xffffffffu, valid ? cv : 0u);                               \
        const uint32_t blk = __ffs(__ballot_sync(0xffffffffu, cv == best)) - 1;                              \
        if (best) sts2(par + PAR_CONST + 56, best, (blk << 7 | (~best >> 2 & 127)) | (all ? 0x1800 : 0x800)); \
        if (all) break;                                                                                      \
        cv = ld_relaxed(inbox);                                                                              \
      }
      while (true) { CAND_STEP(c0) watchdog(n); }
    } else {
      const int t2 = tid - 320;
      mbar_wait(bar_hpub + (warp & 1) * 8, 0);
      PROF(1, t2 == 0, 24);
#pragma unroll 1
      for (int c = 0; c < 8; c++) {
        const uint32_t off = (warp & 1) * UNIT + c * 2048 + lane * 16;
        uint8_t* dst = g_act + (uint32_t)(rb * 80 + cj * 2) * UNIT + off;
        const uint4 v0 = lds4(stage + off), v1 = lds4(stage + off + 512), v2 = lds4(stage + off + 1024), v3 = lds4(stage + off + 1536);
        stg4(dst, v0); stg4(dst + 512, v1); stg4(dst + 1024, v2); stg4(dst + 1536, v3);
      }
      __syncwarp();
      PROF(1, t2 == 0, 15);
      if (lane == 0) {
        mbar_arrive(bar_pread);
        red_release(&g_cnt_h[rb * 32 + cj * 2 + (warp & 1)], 1);
        PROF(1, t2 == 0, 25);
        prefetch_map(&maps.wg); prefetch_map(&maps.wu); prefetch_map(&maps.wd); prefetch_map(&maps.out);
      }
      __syncwarp();
      if (b < NFFN) {
        mbar_wait(bar_go2, 0);
        const __nv_bfloat16* pg = ((b & 1) ? P.w_up : P.w_gate) + (b >> 1) * 64 + (size_t)t2 * FF;
        const __nv_bfloat16* pd = P.w_down + (size_t)b * 32768 + t2 * 64;
        PROF(2, t2 == 0, 13);
#pragma unroll 1
        for (int i = 0; i < WN; i += WB) {
          uint32_t v[WB];
#pragma unroll
          for (int u = 0; u < WB; u++) {
            const int k = i + u;
            asm volatile("ld.global.cg.L2::128B.u32 %0, [%1];" : "=r"(v[u]) : "l"(k < 16 ? pg + (size_t)k * 64 * FF : pd + (k - 16) * 4096));
          }
#pragma unroll
          for (int u = 1; u < WB; u++) v[0] ^= v[u];
          sts1(par + PAR_SINK + t2 * 4, v[0]);
        }
        PROF(2, t2 == 0, 14);
      }
      const uint32_t tag = epoch % 3 + 1;
      mbar_wait(bar_go, 0);
      if (warp == 10) {
        const uint32_t* src = g_mod + 2 * DM + cj * 128 + lane * 4;
        const uint2 wr = *reinterpret_cast<const uint2*>(P.w_r + cj * 128 + lane * 4);
        uint4 vga, vsb, vcb, vgb;
        uint32_t n = 0;
        do {
          vga = ld_relaxed4(src); vsb = ld_relaxed4(src + DM); vcb = ld_relaxed4(src + 2 * DM); vgb = ld_relaxed4(src + 3 * DM);
          watchdog(n);
        } while (!__all_sync(0xffffffffu, tag_ok(vga, tag) && tag_ok(vsb, tag) && tag_ok(vcb, tag) && tag_ok(vgb, tag)));
        const float c0 = rbf(1.f + bf_hi(vcb.x)), c1 = rbf(1.f + bf_hi(vcb.y)), c2 = rbf(1.f + bf_hi(vcb.z)), c3 = rbf(1.f + bf_hi(vcb.w));
        const float a0 = c0 * bf_lo(wr.x), a1 = c1 * bf_hi(wr.x), a2 = c2 * bf_lo(wr.y), a3 = c3 * bf_hi(wr.y);
        const uint32_t h0 = pack_bf(a0, a1), h1 = pack_bf(a2, a3);
        const uint32_t t1 = par + PAR_T1 + (lane >> 2) * 64 + (lane & 1) * 32 + (lane & 2) * 2;
        sts1(t1, h0); sts1(t1 + 8, pack_bf(a0 - bf_lo(h0), a1 - bf_hi(h0)));
        sts1(t1 + 16, h1); sts1(t1 + 24, pack_bf(a2 - bf_lo(h1), a3 - bf_hi(h1)));
        sts4(par + PAR_T2 + lane * 32, make_uint4(pack_bf(c0, c1), __byte_perm(vsb.x, vsb.y, 0x7632), __byte_perm(vgb.x, vgb.y, 0x7632), __byte_perm(vga.x, vga.y, 0x7632)));
        sts4(par + PAR_T2 + lane * 32 + 16, make_uint4(pack_bf(c2, c3), __byte_perm(vsb.z, vsb.w, 0x7632), __byte_perm(vgb.z, vgb.w, 0x7632), __byte_perm(vga.z, vga.w, 0x7632)));
      } else {
        const uint4 g = poll4((lane & 2) ? g_mod + 8 - (lane & 1) * 4 : g_mod + 5 * DM + b * 8 + (lane & 1) * 4, tag);
        sts1(par + PAR_CONST + 60, 0);
        if (lane < 2) sts4(par + PAR_CONST + 16 + lane * 16, g);
        else if (lane < 4) sts2(par + PAR_CONST + (lane - 2) * 8, __float_as_uint(untag_sum(g.x, g.y) + untag_sum(g.z, g.w)), epoch);
      }
      __syncwarp();
#pragma unroll 4
      for (int q = XR; q < XE; q++) st_b128(g_xch + ((size_t)b * 8 * 256 + q * 64 + t2) * 4, (epoch & 1) << 16, 0, 0, 0);
      for (int q = 0; q < 2; q++) st_relaxed4(g_stats + ((size_t)cj * SEQ + rb * 128 + q * 64 + t2) * 4, 0, 0, 0, 0);
      if (b < NFFN)
        for (int q = 0; q < 4; q++) st_relaxed4(g_ypart + ((size_t)(q * 32 + (t2 >> 1)) * NFFN + b) * 8 + (t2 & 1) * 4, 0, 0, 0, 0);
      st_relaxed4(g_row + rb * 2 * DM + (t2 >> 5) * DM + cj * 128 + (t2 & 31) * 4, 0, 0, 0, 0);
      __threadfence();
      mbar_arrive(bar_par);
      mbar_wait(bar_gate, 0);
      uint32_t have = 0, n = 0;
      while (true) {
        const uint32_t st = lds1(par + PAR_CONST + 60) >> 7;
        if ((st & 31) != have) {
          const uint32_t* hsrc = g_row + (st & 15) * 2 * DM + t2 * 4;
          uint4 hv[4];
          bool ok = true;
#pragma unroll
          for (int i = 0; i < 4; i++) hv[i] = ld_pairs(hsrc + i * 256);
#pragma unroll
          for (int i = 0; i < 4; i++) {
            sts2(base + ((FT_G >> i * 4) & 15) * UNIT + (warp & 1) * 8192 + 256 + lane * 8, hv[i].x, hv[i].z);
            ok = ok && hv[i].y == tag && hv[i].w == tag;
          }
          have = __all_sync(0xffffffffu, ok) ? st & 31 : 0;
        }
        if ((st ^ have) == 32) break;
        watchdog(n);
      }
      mbar_arrive(bar_sel);
    }
    __syncwarp();
    cluster_arrive();
    {
      const uint32_t tag = epoch % 3 + 1, t3 = tid - 256;
      mbar_wait(bar_win, 0);
      uint2 win = lds2(par + PAR_CONST + 56);
      win.y &= 0x7ff;
      const uint32_t* fsrc = g_row + (win.y >> 7) * 2 * DM + (b >> 1) * 16 + (t3 & 3) * 4 + (b & 1) * 2;
      const uint32_t* ysrc = g_ypart + (size_t)b * NFFN * 8 + min(t3, NFFN - 1) * 4;
      uint2 fh = ld_pair(fsrc), fx = ld_pair(fsrc + DM);
      if (PSL) __nanosleep(PSL);
      uint4 ya = ld_relaxed4(ysrc), yb = ld_relaxed4(ysrc + NFFN * 4);
      const float rwin = __uint_as_float(((int)win.x < 0 ? win.x & 0x7fffffffu : ~win.x) & ~0x1ffu);
      const float rs = rbf(rcp(1.f + __expf(-rbf(rwin))));
      uint32_t n = 0;
      while (__any_sync(0xffffffffu, fh.y != tag || fx.y != tag)) { fh = ld_pair(fsrc); fx = ld_pair(fsrc + DM); watchdog(n); }
      while (!__all_sync(0xffffffffu, tag_ok(ya, tag) && tag_ok(yb, tag))) {
        if (!tag_ok(ya, tag)) ya = ld_relaxed4(ysrc);
        if (!tag_ok(yb, tag)) yb = ld_relaxed4(ysrc + NFFN * 4);
        watchdog(n);
      }
      __syncwarp();
      PROF(8, t3 == 0, 5);
      float y0 = untag_sum(ya.x, yb.x), y1 = untag_sum(ya.y, yb.y), y2 = untag_sum(ya.z, yb.z), y3 = untag_sum(ya.w, yb.w);
      const bool u1 = lane & 2, u2 = lane & 4;
      y0 = (u1 ? y2 : y0) + __shfl_xor_sync(0xffffffffu, u1 ? y0 : y2, 2);
      y1 = (u1 ? y3 : y1) + __shfl_xor_sync(0xffffffffu, u1 ? y1 : y3, 2);
      y0 = (u2 ? y1 : y0) + __shfl_xor_sync(0xffffffffu, u2 ? y0 : y1, 4);
      y0 += __shfl_xor_sync(0xffffffffu, y0, 8);
      if (!(lane & 8)) sts1(par + PAR_RED + 64 + (t3 >> 4) * 32 + ((lane & 1) * 4 + (lane & 2) + ((lane >> 2) & 1)) * 4, __float_as_uint(y0));
      bar_sync(4, 128);
      if (t3 < 4) {
        y0 = 0.f; y1 = 0.f;
#pragma unroll
        for (int w4 = 0; w4 < 7; w4++) {
          const uint2 v = lds2(par + PAR_RED + 64 + w4 * 32 + t3 * 8);
          y0 += __uint_as_float(v.x); y1 += __uint_as_float(v.y);
        }
        const uint2 gv = lds2(par + PAR_CONST + 16 + t3 * 8);
        const uint32_t upd = hmul2(pack_bf(y0, y1), pack_bf(rs, rs));
        *reinterpret_cast<uint32_t*>(P.out + (size_t)win.y * DM + b * 8 + t3 * 2) =
            hadd2(fx.x, hmul2(__byte_perm(gv.x, gv.y, 0x7632), hadd2(fh.x, upd)));
        if (b == 0 && t3 == 0) st_relaxed(&g_epoch, epoch + 1);
      }
      PROF(31, t3 == 0, 36);
    }
    cluster_wait();
  } else {
    const int wg = warp >> 2;

    uint32_t tag;
    {
      uint32_t* const pmod = g_modp + rank * 2 * DM + (b >> 1) * 32 + lane;
      uint32_t* const pln = g_ln1 + (rb * 128 + cj * 16 + warp) * 4;
      const uint32_t cv = ldg_nc1(P.c + rank * 512 + tid * 2);
      const uint32_t epoch = ld_relaxed(&g_epoch);
      if (warp == 0) st_relaxed(pmod, 0);
      if (lane == 0) { st_b128(pln, 0, 0, 0, 0); st_b128(pln + 32, 0, 0, 0, 0); }
      asm volatile("setmaxnreg.inc.sync.aligned.u32 232;");
      sts1(par + tid * 4, pack_bf(silu_f(bf_lo(cv)), silu_f(bf_hi(cv))));
      bar_sync(1, 320);
      tag = epoch % 3 + 1;
#pragma unroll
      for (int part = 0; part < 3; part++) {
        if (part != 1) {
          const uint32_t xa = base + (2 + part / 2) * GST_BYTES + warp * 2048 + lane * 16;
          mbar_wait(bar_hx + part * 4, 0);
          float s0 = 0.f, s1 = 0.f, q0 = 0.f, q1 = 0.f;
#pragma unroll
          for (int q = 0; q < 4; q++) {
            const uint4 xv = lds4(xa + q * 512);
            const uint32_t u[4] = {xv.x, xv.y, xv.z, xv.w};
#pragma unroll
            for (int e = 0; e < 4; e++) { const float lo = bf_lo(u[e]), hi = bf_hi(u[e]); s0 += lo; s1 += hi; q0 += lo * lo; q1 += hi * hi; }
          }
          s0 += s1; q0 += q1;
#pragma unroll
          for (int o = 16; o > 0; o >>= 1) { s0 += __shfl_xor_sync(0xffffffffu, s0, o); q0 += __shfl_xor_sync(0xffffffffu, q0, o); }
          const float mean = s0 * (1.f / DM);
          float mb, sd;
          ln_scalars(mean, fmaxf(q0 * (1.f / DM) - mean * mean, 0.f), mb, sd);
          uint32_t ih, il;
          split_inv(sd, ih, il);
          if (lane == 0) st_b128(pln + part * 16, pack_bf(mb, mb), ih, il, tag);
          PROF(1, tid == 0 && part == 2, 4);
        } else {
          float acc[8];
#pragma unroll
          for (int e = 0; e < 8; e++) acc[e] = 0.f;
          const uint32_t wa = stage + (tid >> 2) * 64 + (((tid ^ (tid >> 3)) & 3) << 4), sa = par + (tid >> 3) * 4, sh = (tid & 4) ? 0x3244 : 0x1044;
          mbar_wait(bar_hw, 0);
#pragma unroll
          for (int p = 0; p < 8; p++) {
            const uint4 w = lds4(wa + p * 4096);
            const float s = __uint_as_float(__byte_perm(lds1(sa + p * 128), 0, sh));
            acc[0] += s * bf_lo(w.x); acc[1] += s * bf_hi(w.x); acc[2] += s * bf_lo(w.y); acc[3] += s * bf_hi(w.y);
            acc[4] += s * bf_lo(w.z); acc[5] += s * bf_hi(w.z); acc[6] += s * bf_lo(w.w); acc[7] += s * bf_hi(w.w);
          }
#pragma unroll
          for (int e = 0; e < 4; e++) {
            const bool up = lane & 16;
            acc[e] = (up ? acc[e + 4] : acc[e]) + __shfl_xor_sync(0xffffffffu, up ? acc[e] : acc[e + 4], 16);
          }
#pragma unroll
          for (int e = 0; e < 2; e++) {
            const bool up = lane & 8;
            acc[e] = (up ? acc[e + 2] : acc[e]) + __shfl_xor_sync(0xffffffffu, up ? acc[e] : acc[e + 2], 8);
          }
          {
            const bool up = lane & 4;
            acc[0] = (up ? acc[1] : acc[0]) + __shfl_xor_sync(0xffffffffu, up ? acc[0] : acc[1], 4);
          }
          sts1(base + 2 * GST_BYTES + warp * 2048 + ((lane & 3) * 8 + (lane >> 2)) * 4, __float_as_uint(acc[0]));
          bar_sync(1, 256);
          if (warp == 0) {
            float s = 0.f;
#pragma unroll
            for (int w8 = 0; w8 < 8; w8++) s += __uint_as_float(lds1(base + 2 * GST_BYTES + w8 * 2048 + lane * 4));
            st_relaxed(pmod, (__float_as_uint(s) & ~3u) | tag);
          }
          PROF(1, tid == 0, 3);
        }
      }
      cluster_wait();
      if (wg == 1) bar_arrive(2, 256);
    }

    float f0 = 0.f, f1 = 0.f;
    const uint32_t rempty = lane < 2 ? mapa(bempty, lane & 1) : 0;
    constexpr uint32_t GE = NSLOT * 8 + 32;
    float o[64], s[64];
#pragma unroll 1
    for (int ps = 0; ps < 3; ps++) {
      {
        const uint32_t xt = ps == 1 ? XT1 : XT2, wt = ps == 1 ? WT1 : WT2;
        const int nst = ps == 2 ? 28 : 14;
        if (ps == 0) {
          float ga[64], gb[64];
#pragma unroll
          for (int i = 0; i < 64; i++) { ga[i] = 0.f; gb[i] = 0.f; }
          uint32_t a[2][16];
          const uint32_t l = fresh_lane();
          uint32_t fa[4];
#pragma unroll
          for (int kk = 0; kk < 4; kk++) fa[kk] = (base + wg * 8192 + frag_offset(warp)) ^ (kk * 32);
          const uint32_t mt = par + (l & 3) * 16;
          auto fetch = [&](int i, uint32_t (&f)[16], uint32_t z) {
            mbar_wait(xfull + (i & 3) * 8, i >> 2);
#pragma unroll
            for (int kk = 0; kk < 4; kk++) ldmatrix4(fa[kk] + (i & 3) * GST_BYTES + z, f[4 * kk], f[4 * kk + 1], f[4 * kk + 2], f[4 * kk + 3]);
          };
          uint4 r0, r1;
          {
            const uint32_t t7 = (warp & 3) * 32 + l;
            const uint32_t* pm = g_modp + wg * DM + ((cj * 128 + t7 * 4) & (DM - 1));
            const uint32_t* pr = g_ln1 + (rb * 128 + warp * 16 + (l >> 2)) * 4;
            uint4 m0 = ld_relaxed4(pm), m1 = ld_relaxed4(pm + 2 * DM);
            r0 = ld_b128(pr); r1 = ld_b128(pr + 32);
            fetch(0, a[0], 0); fetch(1, a[1], 0);
            uint32_t n = 0;
            bool written = false;
#pragma unroll 1
            while (true) {
              uint32_t miss;
              asm volatile("{ .reg .pred p0, p1, p2, p3; .reg .b32 t, u;\n"
                           "lop3.b32 t, %1, %2, %19, 0x7e; lop3.b32 u, %3, %4, %19, 0x7e; or.b32 t, t, u; and.b32 t, t, 3; setp.ne.u32 p0, t, 0;\n"
                           "lop3.b32 t, %5, %6, %19, 0x7e; lop3.b32 u, %7, %8, %19, 0x7e; or.b32 t, t, u; and.b32 t, t, 3; setp.ne.u32 p1, t, 0;\n"
                           "setp.ne.u32 p2, %12, %19; setp.ne.u32 p3, %16, %19;\n"
                           "@p0 ld.relaxed.gpu.global.v4.u32 {%1, %2, %3, %4}, [%17];\n"
                           "@p1 ld.relaxed.gpu.global.v4.u32 {%5, %6, %7, %8}, [%17 + 8192];\n"
                           "@p2 ld.relaxed.gpu.global.v4.u32 {%9, %10, %11, %12}, [%18];\n"
                           "@p3 ld.relaxed.gpu.global.v4.u32 {%13, %14, %15, %16}, [%18 + 128];\n"
                           "or.pred p0, p0, p1; or.pred p2, p2, p3; vote.sync.any.pred p0, p0, 0xffffffff; vote.sync.any.pred p2, p2, 0xffffffff;\n"
                           "selp.u32 t, 1, 0, p0; selp.u32 u, 2, 0, p2; or.b32 %0, t, u; }"
                           : "=r"(miss), "+r"(m0.x), "+r"(m0.y), "+r"(m0.z), "+r"(m0.w), "+r"(m1.x), "+r"(m1.y), "+r"(m1.z), "+r"(m1.w),
                             "+r"(r0.x), "+r"(r0.y), "+r"(r0.z), "+r"(r0.w), "+r"(r1.x), "+r"(r1.y), "+r"(r1.z), "+r"(r1.w)
                           : "l"(pm), "l"(pr), "r"(tag) : "memory");
              if (!(miss & 1) && !written) {
                written = true;
                float c0 = untag_sum(m0.x, m1.x), c1 = untag_sum(m0.y, m1.y), c2 = untag_sum(m0.z, m1.z), c3 = untag_sum(m0.w, m1.w);
                if (wg) { c0 = 1.f + rbf(c0); c1 = 1.f + rbf(c1); c2 = 1.f + rbf(c2); c3 = 1.f + rbf(c3); }
                const uint32_t d = par + (t7 >> 2) * 64 + (t7 & 1) * 32 + (t7 & 2) * 2 + (wg ? 0 : 8);
                sts1(d, pack_bf(c0, c1));
                sts1(d + 16, pack_bf(c2, c3));
                mbar_arrive(bar_mod);
              }
              if (!miss) break;
              watchdog(n);
            }
          }
          const uint32_t zero = r0.w ^ tag;
          auto normalize = [&](uint32_t (&f)[16]) {
#pragma unroll
            for (int k = 0; k < 16; k += 2) { f[k] = ln_norm(f[k], r0.x, r0.y, r0.z); f[k + 1] = ln_norm(f[k + 1], r1.x, r1.y, r1.z); }
          };
          auto modulate = [&](int i, uint32_t (&f)[16]) {
#pragma unroll
            for (int kk = 0; kk < 4; kk++) {
              const uint4 m = lds4(mt + i * 256 + kk * 64);
              f[4 * kk] = MODUL(f[4 * kk], m.x, m.z); f[4 * kk + 1] = MODUL(f[4 * kk + 1], m.x, m.z);
              f[4 * kk + 2] = MODUL(f[4 * kk + 2], m.y, m.w); f[4 * kk + 3] = MODUL(f[4 * kk + 3], m.y, m.w);
            }
            keep(f);
            mbar_arrive_pred(xempty + (i & 3) * 8, l == 0);
          };
          auto publish = [&](int u, uint32_t (&f)[16]) {
#pragma unroll
            for (int kk = 0; kk < 4; kk++) stmatrix4(fa[kk] + OFF_STAGE + u * UNIT, f[4 * kk], f[4 * kk + 1], f[4 * kk + 2], f[4 * kk + 3]);
            __syncwarp();
            mbar_arrive_pred(bar_hpub + u * 8, l == 0);
          };
          auto multiply = [&](int i, uint32_t (&f)[16]) {
            mbar_wait(gfull + (i & 3) * 8, i >> 2);
            const uint64_t db = make_desc(base + (i & 3) * GST_BYTES + UNIT, 8192, 1024);
            wg_fence();
#pragma unroll
            for (int kk = 0; kk < 4; kk++) mma256_rs(ga, gb, f[4 * kk], f[4 * kk + 1], f[4 * kk + 2], f[4 * kk + 3], db + kk * 128);
            wg_commit();
          };
          auto next = [&](int i, uint32_t (&f)[16]) {
            wg_wait<1>();
            mbar_arrive_cl(rempty, GE + ((i + 2) & 3) * 8);
            uint32_t z = zero;
#pragma unroll
            for (int k = 0; k < 16; k += 2) asm volatile("lop3.b32 %0, %1, %2, %0, 0xA8;" : "+r"(z) : "r"(f[k]), "r"(f[k + 1]));
            fetch(i, f, z);
            normalize(f); modulate(i, f); multiply(i, f);
          };
          normalize(a[0]); normalize(a[1]);
          keep(a[0]); keep(a[1]);
          mbar_wait(bar_mod, 0);
          PROF(1, tid == 0, 2);
          modulate(0, a[0]); multiply(0, a[0]); publish(0, a[0]);
          modulate(1, a[1]); multiply(1, a[1]); publish(1, a[1]);
#pragma unroll 1
          for (int i = 2; i < NRS; i += 2) { next(i, a[0]); next(i + 1, a[1]); }
          wg_wait<1>();
          mbar_arrive_cl(rempty, GE + ((NRS + 2) & 3) * 8);
#pragma unroll 1
          for (int i = NRS; i < 14; i++) {
            mbar_wait(xfull + (i & 3) * 8, (i >> 2) & 1);
            mbar_wait(gfull + (i & 3) * 8, (i >> 2) & 1);
            const uint32_t xa = base + (i & 3) * GST_BYTES;
            const uint64_t da = make_desc(xa + wg * 8192, 16, 1024), db = make_desc(xa + UNIT, 8192, 1024);
            if (i == 13) bar_sync(2 + wg, 256);
            wg_fence();
#pragma unroll
            for (int kk = 0; kk < 4; kk++) mma256_ss(ga, gb, da + kk * 2, db + kk * 128, 1);
            wg_commit();
            if (i == 13) bar_arrive(3 - wg, 256);
            wg_wait<1>();
            uint32_t z = zero;
#pragma unroll
            for (int k = 0; k < 16; k += 2) asm volatile("lop3.b32 %0, %1, %2, %0, 0xA8;" : "+r"(z) : "r"(a[1][k]), "r"(a[1][k + 1]));
            mbar_arrive_cl(rempty, GE + ((i + 3) & 3) * 8 + z);
            mbar_arrive_pred(xempty + ((i + 3) & 3) * 8, l == 0 && i != NRS);
          }
          mbar_wait(xfull + 16, 1);
          wg_wait<0>();
          keep(ga); keep(gb);
#pragma unroll
          for (int i = 0; i < 64; i++) {
            asm volatile("mov.b32 %0, %1;" : "=f"(s[i]) : "f"(ga[i]));
            asm volatile("mov.b32 %0, %1;" : "=f"(o[i]) : "f"(gb[i]));
          }
        } else {
          float ga[64], gb[64];
#pragma unroll
          for (int i = 0; i < 64; i++) {
            asm volatile("mov.b32 %0, %1;" : "=f"(ga[i]) : "f"(s[i]));
            asm volatile("mov.b32 %0, %1;" : "=f"(gb[i]) : "f"(o[i]));
          }
#pragma unroll 1
          for (int i = 0; i < nst; i++) {
            mbar_wait(gfull + (i & 3) * 8, (i >> 2) & 1);
            const uint64_t da = make_desc(base + unit_of(xt, i & 3) + wg * 8192, 16, 1024), db = make_desc(base + unit_of(wt, i & 3), 8192, 1024);
            if (i == nst - 1) bar_sync(2 + wg, 256);
            wg_fence();
#pragma unroll
            for (int kk = 0; kk < 4; kk++) mma256_ss(ga, gb, da + kk * 2, db + kk * 128, kk ? 1 : i);
            wg_commit();
            if (i == nst - 1) bar_arrive(3 - wg, 256);
            wg_wait<1>();
            mbar_arrive_cl(rempty, GE + ((i + 3) & 3) * 8, i != 0);
            PROF(4, tid == 0 && (i & 3) == 0, 40 + (ps - 1) * 4 + i / 4);
          }
          wg_wait<0>();
          keep(ga); keep(gb);
#pragma unroll
          for (int i = 0; i < 64; i++) {
            asm volatile("mov.b32 %0, %1;" : "=f"(s[i]) : "f"(ga[i]));
            asm volatile("mov.b32 %0, %1;" : "=f"(o[i]) : "f"(gb[i]));
          }
        }
        mbar_arrive_cl(rempty, GE + (ps == 2 ? 24 : 8));
        if (ps == 2) break;
      }
      const uint32_t qw = base + wg * 8192, qt = QT >> (16 * ps), at = ps ? AT1 : AT0;
      {
        const uint32_t wt = ps ? WT1 : WT0;
        const uint64_t da0 = make_desc(qw + unit_of(qt, 2), 16, 1024), da1 = make_desc(qw + unit_of(qt, 3), 16, 1024);
        const uint64_t db0 = make_desc(base + unit_of(wt, 2), 8192, 1024), db1 = make_desc(base + unit_of(wt, 3), 8192, 1024);
        mbar_wait(gfull + 16, 1);
        bar_sync(2 + wg, 256);
        wg_fence();
#pragma unroll
        for (int kk = 0; kk < 4; kk++) mma_ss<1>(s, da0 + kk * 2, db0 + kk * 128, 1);
        wg_commit();
        mbar_wait(xfull + 24, 1);
        mbar_wait(gfull + 24, 1);
        wg_fence();
#pragma unroll
        for (int kk = 0; kk < 4; kk++) mma_ss<1>(s, da1 + kk * 2, db1 + kk * 128, 1);
        wg_commit();
        bar_arrive(3 - wg, 256);
        mbar_wait(ps == 0 ? bar_pread : bar_ofree + 8, 0);
        mbar_wait(bfull, 0);
        wg_wait<0>();
        keep(s);
        PROF(2, tid == 0, 8 + ps * 8);
        store_chunk<0>(s, qw + unit_of(qt, 0) + frag_offset(warp));
        store_chunk<1>(s, qw + unit_of(qt, 1) + frag_offset(warp));
        fence_async_smem();
        bar_sync(2 + wg, 256);
        wg_fence();
        issue_qk(s, qw + unit_of(qt, 0), qw + unit_of(qt, 1), base + unit_of(at, 0));
        wg_commit();
#pragma unroll
        for (int kk = 0; kk < 8; kk++) mma_ss<1>(o, (kk < 4 ? da0 : da1) + (kk & 3) * 2, (kk < 4 ? db0 : db1) + UNIT / 16 + (kk & 3) * 128, 1);
        wg_commit();
        bar_arrive(3 - wg, 256);
        wg_wait<1>();
        keep(s);
        mbar_arrive_cl(rempty, 0);
      }
      PROF(4, tid == 0 && ps == 1, 61);
      float l0 = 0.25f, l1 = 0.25f;
      auto step = [&](auto odd_c, const int j, uint32_t (&pw)[32], uint32_t (&pr)[32]) {
        constexpr bool ODD = decltype(odd_c)::value;
        const bool first = !ODD && (j & 2) == 0, last = ODD && j == 7;
        const uint32_t ph = (j >> 1) & 1;
        float i0, i1, a0, a1;
        if (first) { i0 = inv_quad_sum(l0); i1 = inv_quad_sum(l1); l0 = 0.f; l1 = 0.f; }
        bool redo = !ODD && (j | ps) == 0, again = false;
        while (true) {
          if (redo) {
            float m0 = fmaxf(s[0], s[1]), m1 = fmaxf(s[2], s[3]);
#pragma unroll
            for (int i = 1; i < 16; i++) { m0 = fmaxf(m0, fmaxf(s[4 * i], s[4 * i + 1])); m1 = fmaxf(m1, fmaxf(s[4 * i + 2], s[4 * i + 3])); }
            m0 = fmaxf(m0, __shfl_xor_sync(0xffffffffu, m0, 1)); m1 = fmaxf(m1, __shfl_xor_sync(0xffffffffu, m1, 1));
            m0 = fmaxf(m0, __shfl_xor_sync(0xffffffffu, m0, 2)); m1 = fmaxf(m1, __shfl_xor_sync(0xffffffffu, m1, 2));
            m0 *= SCL2; m1 *= SCL2;
            if (!first) {
              m0 = fmaxf(m0, f0); m1 = fmaxf(m1, f1);
              const float c0 = ex2(f0 - m0), c1 = ex2(f1 - m1);
              l0 *= c0; l1 *= c1;
              wg_wait<0>();
              keep(o);
#pragma unroll
              for (int i = 0; i < 16; i++) { o[4 * i] *= c0; o[4 * i + 1] *= c0; o[4 * i + 2] *= c1; o[4 * i + 3] *= c1; }
            }
            f0 = m0; f1 = m1;
          }
          float b0 = 0.f, b1 = 0.f;
          a0 = 0.f; a1 = 0.f;
#pragma unroll
          for (int i = 0; i < 16; i++) {
            const float e0 = ex2(fmaf(s[4 * i], SCL2, -f0)), e1 = ex2(fmaf(s[4 * i + 1], SCL2, -f0));
            const float e2 = ex2(fmaf(s[4 * i + 2], SCL2, -f1)), e3 = ex2(fmaf(s[4 * i + 3], SCL2, -f1));
            a0 += e0; b0 += e1; a1 += e2; b1 += e3;
            pw[2 * i] = pack_bf(e0, e1); pw[2 * i + 1] = pack_bf(e2, e3);
            if (i == VREL) {
#pragma unroll
              for (int k = 0; k < 2 * VREL + 2; k++) asm volatile("" : "+r"(pw[k])::"memory");
              mbar_wait(bar_mod, 0);
              wg_wait<0>();
              mbar_arrive_cl(rempty, ODD ? 16 : (j ? 0 : GE + 16), !again);
              if (!ODD) mbar_arrive_cl(rempty, GE + 24, !again && j == 0);
#pragma unroll
              for (int k = 4 * VREL + 4; k < 64; k++) asm volatile("" : "+f"(s[k])::"memory");
            }
          }
          a0 += b0; a1 += b1;
          if (redo) break;
          redo = __any_sync(0xffffffffu, !(a0 + a1 < 0x1p70f));
          if (first) {
            uint32_t m0 = __ballot_sync(0xffffffffu, a0 > 0x1p-50f), m1 = __ballot_sync(0xffffffffu, a1 > 0x1p-50f);
            m0 |= m0 >> 1; m1 |= m1 >> 1; m0 |= m0 >> 2; m1 |= m1 >> 2;
            redo = redo || (m0 & m1 & 0x11111111u) != 0x11111111u;
          }
          if (!redo) break;
          again = true;
        }
        l0 += a0; l1 += a1;
        keep(pw);
        keep(o);
        const uint32_t qo = qt >> (j ? 0 : 8);
        if (first) store_chunk<0>(o, i0, i1, qw + unit_of(qo, 0) + frag_offset(warp));
        keep(o);
        mbar_wait(bfull + (ODD ? 24 : 8), ph);
        bar_sync(2 + wg, 256);
        if (!last) {
          const uint32_t qn = qt >> (j >= 3 ? 8 : 0);
          wg_fence();
          issue_qk(s, qw + unit_of(qn, 0), qw + unit_of(qn, 1), base + unit_of(at, ODD ? 3 : 1));
          wg_commit();
          mbar_wait(bfull + (ODD ? 0 : 16), ODD ? ph ^ 1 : ph);
        }
        if (first) { store_chunk<1>(o, i0, i1, qw + unit_of(qo, 1) + frag_offset(warp)); keep(o); }
        wg_fence();
        issue_pv(o, pw, base + unit_of(at, ODD ? (last ? 3 : 0) : 2), !first);
        wg_commit();
        bar_arrive(3 - wg, 256);
        wg_wait<1>();
        keep(s);
        mbar_arrive_cl(rempty, ODD ? 24 : 8, !last);
        if (first) { fence_async_smem(); mbar_arrive_pred(bar_ofull + wg * 8, j); }
        PROF(4, tid == 0 && ps == 1, 51 + j);
      };
      uint32_t pa[32], pb[32];
#pragma unroll 1
      for (int j = 0; j < 8; j += 2) {
        step(std::false_type{}, j, pa, pb);
        step(std::true_type{}, j + 1, pb, pa);
      }
      {
        const float i0 = inv_quad_sum(l0), i1 = inv_quad_sum(l1);
        wg_wait<0>();
        keep(o);
        mbar_arrive_cl(rempty, 24);
        store_chunk<0>(o, i0, i1, qw + unit_of(qt, 2) + frag_offset(warp));
        store_chunk<1>(o, i0, i1, qw + unit_of(qt, 3) + frag_offset(warp));
        fence_async_smem();
        mbar_arrive(bar_ofull + 16 + wg * 8);
      }
      PROF(2, tid == 0, 10 + ps * 8);
    }

    const int ln = fresh_lane(), g = ln >> 2, tq = ln & 3, ct = warp * 32 + ln;
    const bool lane0 = ln == 0;
    const int lrow0 = warp * 16 + g;
    const int grow0 = rb * 128 + lrow0;
    const uint32_t res = base + OFF_RES, trow = res + wg * 8192 + frag_offset(warp);
    uint32_t xr[32];
    uint4 sv[4], own;
    uint32_t* sp[4];
#pragma unroll
    for (int k = 0; k < 4; k++) sp[k] = g_stats + ((((tq >> 1) * 4 + k) ^ cj) * SEQ + grow0 + (tq & 1) * 8) * 4;
    {
      const uint64_t da = make_desc(base + wg * 8192, 16, 1024), db = make_desc(base, 8192, 1024);
      constexpr int U = UNIT / 16;
#define HALF_STAGE(acc, xu, wu) _Pragma("unroll") for (int kk = 0; kk < 4; kk++) mma_ss<1>(acc, da + (xu) * U + kk * 2, db + (wu) * U + kk * 128, 1)
      PROF(10, ct == PT, 19); STAMP(0);
      cluster_arrive();
      mbar_wait(gfull, 1);
      mbar_wait(gfull + 8, 1);
      bar_sync(2 + wg, 256);
      wg_fence();
      HALF_STAGE(o, 7, 1);
      HALF_STAGE(o, 8, 3);
      wg_commit();
      STAMP(16);
      mbar_wait(gfull + 16, 1);
      STAMP(17);
      wg_fence();
      HALF_STAGE(o, 6, 11);
      wg_commit();
      bar_arrive(3 - wg, 256);
      mbar_wait(bar_par, 0);
      uint32_t* xo = g_xch + ((size_t)b * 8 * 256 + ct) * 4;
      const uint32_t* xi = g_xch + ((size_t)(b ^ 2) * 8 * 256 + ct) * 4;
      const uint32_t par1 = (~lds1(par + PAR_CONST + 4) & 1) << 16;
      uint32_t ga[16];
      uint4 bw[8];
#define LOAD_PAR _Pragma("unroll") for (int i = 0; i < 8; i++) {                                                               \
        ga[2 * i] = lds1(par + PAR_T2 + i * 128 + tq * 16 + 12); ga[2 * i + 1] = lds1(par + PAR_T2 + i * 128 + 64 + tq * 16 + 12); \
        bw[i] = lds4(par + PAR_T1 + i * 64 + tq * 16);                                                                          \
        if (!(g & 1)) { bw[i].x = 0x3f803f80u; bw[i].y = 0x3f803f80u; }                                                         \
      }
      if (PPOS == 0) LOAD_PAR
      wg_wait<1>();
      mbar_arrive_pred(bar_rel, lane0);
      wg_wait<0>();
      keep(o);
      mbar_arrive_pred(bar_ring, lane0);
      PROF(8, ct == PT, 20); STAMP(1);
#define SEND(i) st_b128(xo + (i) * 1024, (pack_bf(o[8 * (i)], o[8 * (i) + 1]) & ~0x10000u) | par1, pack_bf(o[8 * (i) + 2], o[8 * (i) + 3]), \
                        pack_bf(o[8 * (i) + 4], o[8 * (i) + 5]), pack_bf(o[8 * (i) + 6], o[8 * (i) + 7]))
#pragma unroll
      for (int i = 0; i < NS1; i++) SEND(i);
      PROF(8, ct == PT, 21); STAMP(2);
      bar_sync(2 + wg, 256);
      wg_fence();
      HALF_STAGE(s, 7, 0);
      HALF_STAGE(s, 8, 2);
      HALF_STAGE(s, 6, 10);
      wg_commit();
      bar_arrive(3 - wg, 256);
      STAMP(18);
      mbar_wait(gfull + 24, 1);
#pragma unroll
      for (int i = NS1; i < 8; i++) SEND(i);
      uint4 v[8];
#pragma unroll
      for (int i = 0; i < 4; i++) v[i] = ld_b128(xi + i * 1024);
      if (PPOS == 1) LOAD_PAR
      STAMP(19);
      mbar_wait(bar_xres, 0);
      wg_wait<0>();
      mbar_arrive_pred(bar_ring + 8, lane0);
      bar_sync(2 + wg, 256);
      STAMP(20);
#pragma unroll
      for (int i = 4; i < 8; i++) v[i] = ld_b128(xi + i * 1024);
      mbar_wait(bar_xres, 0);
      wg_fence();
      HALF_STAGE(s, 9, 4);
      wg_commit();
      mbar_wait(bar_rx, 0);
      wg_fence();
      HALF_STAGE(s, 1, 5);
      wg_commit();
      bar_arrive(3 - wg, 256);
      STAMP(21);
      wg_wait<0>();
      keep(s);
      mbar_arrive_pred(bar_ring + 16, lane0);
      PROF(10, ct == PT, 23); STAMP(4);
#pragma unroll
      for (int i = 0; i < 16; i += 2) ldmatrix4((trow ^ ((i & 7) << 4)) + (i >> 3) * 16384, xr[2 * i], xr[2 * i + 1], xr[2 * i + 2], xr[2 * i + 3]);
      if (PPOS == 2) LOAD_PAR
      uint32_t pk[32];
      pack_p(s, pk);
      keep(pk);
      {
        uint32_t n = 0, miss;
        do {
          miss = 0;
#pragma unroll
          for (int i = 0; i < 8; i++) miss |= v[i].x ^ par1;
          miss = __any_sync(0xffffffffu, miss & 0x10000u);
          if (miss) {
#pragma unroll
            for (int i = 0; i < 8; i++)
              asm volatile("{ .reg .pred p; .reg .b32 t; xor.b32 t, %0, %5; and.b32 t, t, 0x10000; setp.ne.u32 p, t, 0;\n"
                           "@p ld.relaxed.gpu.global.v4.u32 {%0, %1, %2, %3}, [%4]; }"
                           : "+r"(v[i].x), "+r"(v[i].y), "+r"(v[i].z), "+r"(v[i].w) : "l"(xi + i * 1024), "r"(par1) : "memory");
          }
          watchdog(n);
        } while (miss);
      }
      PROF(8, ct == PT, 22); STAMP(3);
#pragma unroll
      for (int k = 0; k < 4; k++) sv[k] = ESV ? ld_b128(sp[k]) : make_uint4(0, 0, 0, 0);
      float ds[4] = {0.f, 0.f, 0.f, 0.f}, dl[4] = {0.f, 0.f, 0.f, 0.f}, q0[4] = {0.f, 0.f, 0.f, 0.f}, q1[4] = {0.f, 0.f, 0.f, 0.f};
#pragma unroll
      for (int i = 0; i < 8; i++) {
        const uint32_t u0 = hfma2(ga[2 * i], hadd2(pk[4 * i], v[i].x & ~0x10000u), xr[4 * i]);
        const uint32_t u1 = hfma2(ga[2 * i], hadd2(pk[4 * i + 1], v[i].y), xr[4 * i + 1]);
        const uint32_t u2 = hfma2(ga[2 * i + 1], hadd2(pk[4 * i + 2], v[i].z), xr[4 * i + 2]);
        const uint32_t u3 = hfma2(ga[2 * i + 1], hadd2(pk[4 * i + 3], v[i].w), xr[4 * i + 3]);
        xr[4 * i] = u0; xr[4 * i + 1] = u1; xr[4 * i + 2] = u2; xr[4 * i + 3] = u3;
        mma16816(ds, u0, u1, u2, u3, bw[i].x, bw[i].y);
        mma16816(dl, u0, u1, u2, u3, bw[i].z, bw[i].w);
        mma16816(q0, u0, u1, u2, u3, u0, u2);
        mma16816(q1, u0, u1, u2, u3, u1, u3);
      }
      const float sqa = __shfl_sync(0xffffffffu, (g & 1) ? q0[1] : q0[0], g * 4 + (g >> 1));
      const float sqb = __shfl_sync(0xffffffffu, (g & 1) ? q1[3] : q1[2], g * 4 + (g >> 1));
      own = (tq & 1) ? make_uint4(__float_as_uint(ds[2]), __float_as_uint(sqb), __float_as_uint(ds[3] + dl[3]), tag)
                                 : make_uint4(__float_as_uint(ds[0]), __float_as_uint(sqa), __float_as_uint(ds[1] + dl[1]), tag);
      if (tq < 2) st_b128(sp[0], own.x, own.y, own.z, own.w);
    }
    PROF(8, ct == PT, 29); STAMP(5);
    uint32_t mm, ih, il;
    float rbest;
    uint32_t wf[128];
    const uint32_t frow = (ln & 7) + (ln >> 4) * 8;
    const uint32_t wfo = base + (warp & 1) * 8192 + frow * 64 + ((((ln >> 3) & 1) ^ ((frow >> 1) & 3)) << 4);
#define LOAD_WF(m) _Pragma("unroll") for (int f = 0; f < 16; f++) {                                                   \
      const int r = ((f >> 1) * 4 + (m) * 2 + (f & 1)) * 4;                                                           \
      ldmatrix4t(((wfo + unit_of((m) ? FT_U : FT_G, warp >> 1)) ^ ((f & 1) * 32)) + (f >> 1) * 1024, wf[r], wf[r + 1], wf[r + 2], wf[r + 3]); \
    }
    bool early, wait1;
    {
#pragma unroll
      for (int i = 0; i < 16; i += 2) stmatrix4((trow ^ ((i & 7) << 4)) + (i >> 3) * 16384, xr[2 * i], xr[2 * i + 1], xr[2 * i + 2], xr[2 * i + 3]);
      const uint4 cst = lds4(par + PAR_CONST);
      const float A1 = __uint_as_float(cst.x), A2 = __uint_as_float(cst.z);
      uint32_t n = 0;
      early = false; wait1 = false;
#pragma unroll 1
      while (true) {
        uint32_t miss;
        asm volatile("{ .reg .pred p0, p1, p2, p3; .reg .b64 u, v; .reg .b128 w;\n"
                     "setp.ge.u32 p0, %22, 2; setp.ne.and.u32 p0, %4, %21, p0; setp.ne.u32 p1, %8, %21; setp.ne.u32 p2, %12, %21; setp.ne.u32 p3, %16, %21;\n"
                     "@p0 ld.relaxed.gpu.global.v4.u32 {%1, %2, %3, %4}, [%17];\n"
                     "@p1 ld.relaxed.gpu.global.v4.u32 {%5, %6, %7, %8}, [%18];\n"
                     "@p2 ld.relaxed.gpu.global.v4.u32 {%9, %10, %11, %12}, [%19];\n"
                     "@p3 ld.relaxed.gpu.global.v4.u32 {%13, %14, %15, %16}, [%20];\n"
                     "or.pred p0, p0, p1; or.pred p2, p2, p3; or.pred p0, p0, p2; vote.sync.any.pred p0, p0, 0xffffffff; selp.u32 %0, 1, 0, p0; }"
                     : "=r"(miss), "+r"(sv[0].x), "+r"(sv[0].y), "+r"(sv[0].z), "+r"(sv[0].w), "+r"(sv[1].x), "+r"(sv[1].y), "+r"(sv[1].z), "+r"(sv[1].w),
                       "+r"(sv[2].x), "+r"(sv[2].y), "+r"(sv[2].z), "+r"(sv[2].w), "+r"(sv[3].x), "+r"(sv[3].y), "+r"(sv[3].z), "+r"(sv[3].w)
                     : "l"(sp[0]), "l"(sp[1]), "l"(sp[2]), "l"(sp[3]), "r"(tag), "r"(tq) : "memory");
        if (!miss) break;
        wait1 = true;
        if (!early && (b >= NFFN || __all_sync(0xffffffffu, mbar_test(bar_box + (warp >> 1) * 8, 0)))) {
          early = true;
          LOAD_WF(0);
          __syncwarp();
          mbar_arrive_pred(bar_gate, lane0);
        }
        watchdog(n);
      }
      const uint4 v0 = tq < 2 ? own : sv[0], v1 = sv[1], v2 = sv[2], v3 = sv[3];
      PROF(8, ct == PT, 30); STAMP(6);
      float su = (__uint_as_float(v0.x) + __uint_as_float(v1.x)) + (__uint_as_float(v2.x) + __uint_as_float(v3.x));
      float sq = (__uint_as_float(v0.y) + __uint_as_float(v1.y)) + (__uint_as_float(v2.y) + __uint_as_float(v3.y));
      float dt = (__uint_as_float(v0.z) + __uint_as_float(v1.z)) + (__uint_as_float(v2.z) + __uint_as_float(v3.z));
      su += __shfl_xor_sync(0xffffffffu, su, 2); sq += __shfl_xor_sync(0xffffffffu, sq, 2); dt += __shfl_xor_sync(0xffffffffu, dt, 2);
      const float m = su * (1.f / DM);
      float mb, sd;
      ln_scalars(m, fmaxf(sq * (1.f / DM) - m * m, 0.f), mb, sd);
      const float inv = rcp(sd);
      rbest = (dt - mb * A1) * inv + A2;
      mm = pack_bf(mb, mb);
      ih = pack_bf(inv, inv);
      const float lo = inv - bf_lo(ih);
      il = pack_bf(lo, lo);
    }
    int ibest;
    {
      const uint32_t bits = __float_as_uint(rbest);
      const uint32_t key = (((int)bits < 0 ? ~bits : bits | 0x80000000u) & ~0x1ffu) | ((127 - lrow0 - (tq & 1) * 8) << 2) | tag;
      sts1(par + PAR_RED + warp * 4, __reduce_max_sync(0xffffffffu, key));
      PROF(8, ct == PT, 38); STAMP(7);
      uint32_t waited;
      asm volatile("{ .reg .pred p, q; setp.ne.u32 p, %1, 0; barrier.cta.red.or.pred q, 1, 256, p; selp.u32 %0, 1, 0, q; }" : "=r"(waited) : "r"((uint32_t)(wait1 && (wg || CW0))) : "memory");
      const uint4 ka = lds4(par + PAR_RED), kb = lds4(par + PAR_RED + 16);
      const uint32_t k2 = max(max(max(ka.x, ka.y), max(ka.z, ka.w)), max(max(kb.x, kb.y), max(kb.z, kb.w)));
      if (ct == 0 && ((cj & CWM) == 0 || (CWL && !waited))) st_relaxed(g_cand + rb, k2);
      ibest = 127 - ((k2 >> 2) & 127);
    }
    PROF(8, ct == PT, 39); STAMP(8);
    if ((ibest >> 4) == warp) {
      const int src = (ibest & 7) * 4 + ((ibest >> 3) & 1), ch = g * 2;
      const uint32_t cm = __shfl_sync(0xffffffffu, mm, src), ch_ = __shfl_sync(0xffffffffu, ih, src), cl = __shfl_sync(0xffffffffu, il, src);
      const uint32_t xa = res + (ch >> 3) * 16384 + ibest * 128 + (((ch & 7) ^ (ibest & 7)) << 4) + tq * 4;
      const uint32_t x0 = lds1(xa), x1 = lds1(xa ^ 16);
      const uint2 p0 = lds2(par + PAR_T2 + ch * 64 + tq * 16), p1 = lds2(par + PAR_T2 + ch * 64 + 64 + tq * 16);
      uint32_t* dst = g_row + rb * 2 * DM + cj * 128 + ln * 4;
      st_pairs(dst, ln_mod(x0, cm, ch_, cl, p0.x, p0.y), ln_mod(x1, cm, ch_, cl, p1.x, p1.y), tag);
      st_pairs(dst + DM, x0, x1, tag);
      __syncwarp();
    }
    PROF(8, ct == PT, 37); STAMP(9);
    uint32_t wd[64];
    const uint32_t wda = base + unit_of(FT_D, warp >> 1) + (warp & 1) * 8192 + frow * 128 + ((((ln >> 3) & 1) ^ (ln & 7)) << 4);
#define LOAD_WD(f) ldmatrix4t((wda ^ ((((f) >> 1) & 3) * 32)) + ((f) >> 3) * 4096 + ((f) & 1) * 2048, wd[4 * (f)], wd[4 * (f) + 1], wd[4 * (f) + 2], wd[4 * (f) + 3])
    if (!early) {
      if (b < NFFN) mbar_wait(bar_box + (warp >> 1) * 8, 0);
      LOAD_WF(0);
      __syncwarp();
      mbar_arrive_pred(bar_gate, lane0);
    }
    if (b < NFFN) {
      const uint32_t own = base + unit_of(FT_G, warp >> 1) + (warp & 1) * 8192;
      mbar_wait(bar_box + (4 + (warp >> 1)) * 8, 0);
      LOAD_WF(1);
      uint32_t* const ydst = g_ypart + ((size_t)(warp * 16 + tq * 2) * NFFN + b) * 8 + g;
      PROF(8, ct == PT, 31); STAMP(10);
      mbar_wait(bar_box + (8 + (warp >> 1)) * 8, 0);
#pragma unroll
      for (int f = 0; f < WDE; f++) LOAD_WD(f);
      STAMP(11);
      mbar_wait(bar_sel, 0);
      PROF(8, ct == PT, 33); STAMP(12);
      float d[8][4];
#pragma unroll
      for (int i = 0; i < 4; i++) { d[i][0] = 0.f; d[i][1] = 0.f; d[i][2] = 0.f; d[i][3] = 0.f; }
#pragma unroll
      for (int ks = 0; ks < 8; ks++) {
        const uint2 hb = lds2(own + 256 + ks * 32 + tq * 8);
#pragma unroll
        for (int mt = 0; mt < 4; mt++) {
          const int r = ks * 16 + mt * 4;
          mma16816(d[mt], wf[r], wf[r + 1], wf[r + 2], wf[r + 3], hb.x, hb.y);
        }
      }
      sts2(own + (tq * 8 + g) * 8, __float_as_uint((tq & 2) ? ((tq & 1) ? d[1][2] : d[1][0]) : ((tq & 1) ? d[0][2] : d[0][0])),
           __float_as_uint((tq & 2) ? ((tq & 1) ? d[3][2] : d[3][0]) : ((tq & 1) ? d[2][2] : d[2][0])));
      bar_sync(1, 256);
      uint32_t ab[4];
      {
        float G = 0.f, U = 0.f;
        uint2 pv[8];
#pragma unroll
        for (int w8 = 0; w8 < 8; w8++) pv[w8] = lds2(base + ln * 8 + ((FT_G >> (w8 >> 1) * 4) & 15) * UNIT + (w8 & 1) * 8192);
#pragma unroll
        for (int w8 = 0; w8 < 8; w8 += 2) {
          G += __uint_as_float(pv[w8].x) + __uint_as_float(pv[w8 + 1].x);
          U += __uint_as_float(pv[w8].y) + __uint_as_float(pv[w8 + 1].y);
        }
#pragma unroll
        for (int f = WDE; f < 16; f++) LOAD_WD(f);
        const float act = rbf(silu_f(rbf(G))) * rbf(U);
        const uint32_t pk = pack_bf(act, __shfl_down_sync(0xffffffffu, act, 1));
#pragma unroll
        for (int i = 0; i < 4; i++) ab[i] = __shfl_sync(0xffffffffu, pk, i * 8 + tq * 2);
      }
      PROF(8, ct == PT, 34); STAMP(13);
#pragma unroll
      for (int mt = 0; mt < 8; mt++) {
        d[mt][0] = 0.f; d[mt][1] = 0.f; d[mt][2] = 0.f; d[mt][3] = 0.f;
        mma16816(d[mt], wd[mt * 8], wd[mt * 8 + 1], wd[mt * 8 + 2], wd[mt * 8 + 3], ab[0], ab[1]);
        mma16816(d[mt], wd[mt * 8 + 4], wd[mt * 8 + 5], wd[mt * 8 + 6], wd[mt * 8 + 7], ab[2], ab[3]);
      }
#pragma unroll
      for (int i = 0; i < 4; i++) {
        const int m4 = (i >> 1) * 4, e = (i & 1) * 2;
        const float y = (tq & 2) ? ((tq & 1) ? d[m4 + 3][e] : d[m4 + 2][e]) : ((tq & 1) ? d[m4 + 1][e] : d[m4][e]);
        st_relaxed(ydst + (m4 * 2 + (i & 1)) * NFFN * 8, tagf(y, tag));
      }
      PROF(8, ct == PT, 35); STAMP(14);
    }
    mbar_wait(bar_sel, 0);
    mbar_arrive_pred(bar_win, ct == 0);
    const int iwin = lds1(par + PAR_CONST + 60) & 0x7ff;
    const bool cand = (iwin >> 4) == rb * 8 + warp;
    {
      const uint32_t mm0 = __shfl_sync(0xffffffffu, mm, ln & ~1), mm1 = __shfl_sync(0xffffffffu, mm, ln | 1);
      const uint32_t ih0 = __shfl_sync(0xffffffffu, ih, ln & ~1), ih1 = __shfl_sync(0xffffffffu, ih, ln | 1);
      const uint32_t il0 = __shfl_sync(0xffffffffu, il, ln & ~1), il1 = __shfl_sync(0xffffffffu, il, ln | 1);
#pragma unroll 1
      for (int hf = 0; hf < 2; hf++) {
        uint32_t x[16];
#pragma unroll
        for (int i = 0; i < 8; i += 2) ldmatrix4((trow ^ (i << 4)) + hf * 16384, x[2 * i], x[2 * i + 1], x[2 * i + 2], x[2 * i + 3]);
#pragma unroll
        for (int i = 0; i < 8; i++) {
          const uint4 pv = lds4(par + PAR_T2 + (hf * 8 + i) * 64 + tq * 16);
          x[2 * i] = hadd2(x[2 * i], hmul2(pv.z, ln_mod(x[2 * i], mm0, ih0, il0, pv.x, pv.y)));
          x[2 * i + 1] = hadd2(x[2 * i + 1], hmul2(pv.z, ln_mod(x[2 * i + 1], mm1, ih1, il1, pv.x, pv.y)));
        }
#pragma unroll
        for (int i = 0; i < 8; i += 2) stmatrix4((trow ^ (i << 4)) + hf * 16384, x[2 * i], x[2 * i + 1], x[2 * i + 2], x[2 * i + 3]);
      }
      if (!cand) fence_async_smem();
      __syncwarp();
      if (!cand && elect_one()) {
        tma2d_store(&maps.out, res + warp * 2048, cj * 128, rb * 128 + warp * 16);
        tma2d_store(&maps.out, res + 16384 + warp * 2048, cj * 128 + 64, rb * 128 + warp * 16);
        asm volatile("cp.async.bulk.commit_group;" ::: "memory");
      }
    }
    if (cand) {
      const int wrow0 = warp * 16;
#pragma unroll 2
      for (int p = 0; p < 8; p++) {
        const int row = 2 * p + (ln >> 4), ch = ln & 15;
        const uint4 v = lds4(res + (ch >> 3) * 16384 + (wrow0 + row) * 128 + (((ch & 7) ^ (row & 7)) << 4));
        if (rb * 128 + wrow0 + row != iwin) *reinterpret_cast<uint4*>(P.out + (size_t)(rb * 128 + wrow0 + row) * DM + cj * 128 + ch * 8) = v;
      }
    }
    asm volatile("cp.async.bulk.wait_group.read 0;" ::: "memory");
    PROF(8, ct == PT, 11); STAMP(15);
    cluster_wait();
  }
}

typedef CUresult (*EncodeFn)(CUtensorMap*, CUtensorMapDataType, cuuint32_t, void*, const cuuint64_t*, const cuuint64_t*,
                             const cuuint32_t*, const cuuint32_t*, CUtensorMapInterleave, CUtensorMapSwizzle,
                             CUtensorMapL2promotion, CUtensorMapFloatOOBfill);

void map2d(EncodeFn enc, CUtensorMap* m, const void* p, uint64_t rows, uint64_t cols, uint32_t brows) {
  cuuint64_t dims[2] = {cols, rows}, strides[1] = {cols * 2};
  cuuint32_t box[2] = {64, brows}, es[2] = {1, 1};
  enc(m, CU_TENSOR_MAP_DATA_TYPE_BFLOAT16, 2, const_cast<void*>(p), dims, strides, box, es, CU_TENSOR_MAP_INTERLEAVE_NONE,
      CU_TENSOR_MAP_SWIZZLE_128B, CU_TENSOR_MAP_L2_PROMOTION_L2_256B, CU_TENSOR_MAP_FLOAT_OOB_FILL_NONE);
}
void map2d_narrow(EncodeFn enc, CUtensorMap* m, const void* p, uint64_t rows, uint64_t cols, uint32_t brows) {
  cuuint64_t dims[2] = {cols, rows}, strides[1] = {cols * 2};
  cuuint32_t box[2] = {32, brows}, es[2] = {1, 1};
  enc(m, CU_TENSOR_MAP_DATA_TYPE_BFLOAT16, 2, const_cast<void*>(p), dims, strides, box, es, CU_TENSOR_MAP_INTERLEAVE_NONE,
      CU_TENSOR_MAP_SWIZZLE_64B, CU_TENSOR_MAP_L2_PROMOTION_L2_64B, CU_TENSOR_MAP_FLOAT_OOB_FILL_NONE);
}
void map3d(EncodeFn enc, CUtensorMap* m, const void* p, uint64_t rows, uint64_t cols, uint32_t brows, uint32_t nch) {
  cuuint64_t dims[3] = {64, rows, cols / 64}, strides[2] = {cols * 2, 128};
  cuuint32_t box[3] = {64, brows, nch}, es[3] = {1, 1, 1};
  enc(m, CU_TENSOR_MAP_DATA_TYPE_BFLOAT16, 3, const_cast<void*>(p), dims, strides, box, es, CU_TENSOR_MAP_INTERLEAVE_NONE,
      CU_TENSOR_MAP_SWIZZLE_128B, CU_TENSOR_MAP_L2_PROMOTION_L2_256B, CU_TENSOR_MAP_FLOAT_OOB_FILL_NONE);
}

}

extern "C" void kernel_launch(void* const* d_in, const int* in_sizes, int n_in, void* d_out, int out_size) {
  (void)in_sizes; (void)n_in; (void)out_size;
  static EncodeFn enc = nullptr;
  if (!enc) {
    void* fn = nullptr;
    cudaDriverEntryPointQueryResult st;
    cudaGetDriverEntryPoint("cuTensorMapEncodeTiled", &fn, cudaEnableDefault, &st);
    enc = (EncodeFn)fn;
    cudaFuncSetAttribute(fused_kernel, cudaFuncAttributeMaxDynamicSharedMemorySize, SMEM_BYTES);
  }
  Maps maps;
  map2d(enc, &maps.x, d_in[0], SEQ, DM, 128);
  map2d(enc, &maps.out, d_out, SEQ, DM, 16);
  map3d(enc, &maps.wq, d_in[3], DM, NQ, 64, 2);
  map3d(enc, &maps.k, d_in[1], 4 * SK, 128, 128, 1);
  map3d(enc, &maps.v, d_in[2], 4 * SK, 128, 128, 1);
  map3d(enc, &maps.wo, d_in[4], NQ, DM, 64, 2);
  map2d_narrow(enc, &maps.wg, d_in[7], DM, FF, 256);
  map2d_narrow(enc, &maps.wu, d_in[8], DM, FF, 256);
  map3d(enc, &maps.wd, d_in[9], FF, DM, 32, 4);
  map2d_narrow(enc, &maps.wm, d_in[11], DM, NMOD, 256);
  Ptrs p;
  p.x = (const __nv_bfloat16*)d_in[0];
  p.w_r = (const __nv_bfloat16*)d_in[6];
  p.w_gate = (const __nv_bfloat16*)d_in[7];
  p.w_up = (const __nv_bfloat16*)d_in[8];
  p.w_down = (const __nv_bfloat16*)d_in[9];
  p.c = (const __nv_bfloat16*)d_in[10];
  p.w_mod = (const __nv_bfloat16*)d_in[11];
  p.out = (__nv_bfloat16*)d_out;
  fused_kernel<<<NMAIN + NHELP, 384, SMEM_BYTES>>>(maps, p);
}
```

```cpp
#include <cuda_runtime.h>
#include <cuda_bf16.h>
#include <cuda.h>
#include <stdint.h>
#include <type_traits>

#define HD 2
#define HDX 2
#define XF 4
#define XE 32
#define XR 0
#define NRS 8
#define FPACE 3
#define GOST 20
#define WB 3
#define WN 24
#define RES0 17
#define RES1 20
#define HU 32
#define NS1 6
#define PG0 0
#define PSL 0
#define CWM 7
#define WDE 16
#define CWL 1
#define CW0 0
#define ESV 1
#define PPOS 1
#define FB0 0
#define FB2 8
#define OPS 8192
#define OFL 0
#define ODS 8
#define MODUL hfma2
#define LNP 1
#define OMUL hfma2
#define VREL 7
#define E0 3

namespace {

constexpr int SEQ = 2048, DM = 1024, NQ = 4096, SK = 2048, WIN = 512, FF = 3584, NMOD = 6144;
constexpr int NMAIN = 128, NHELP = 4, NFFN = 112;
constexpr int NSLOT = 4, SLOT_BYTES = 32768, UNIT = 16384, GST_BYTES = 3 * UNIT;
constexpr uint32_t XT1 = 0xDCBA, XT2 = 0x9687;
constexpr uint32_t WT0 = 0xA741, WT1 = 0x7420, WT2 = 0x4A20;
constexpr uint32_t AT0 = WT1, AT1 = WT2;
constexpr uint32_t QT = 0xDC9696DC;
constexpr int OFF_STAGE = 12 * UNIT;
constexpr uint32_t FT_G = 0x07B3, FT_U = 0xA628, FT_D = 0x5149;
constexpr int OFF_RES = 12 * UNIT;
constexpr int OFF_PAR = 14 * UNIT;
constexpr int OFF_BAR = OFF_PAR + 2528;
constexpr int SMEM_BYTES = OFF_BAR + 544;
static_assert(SMEM_BYTES <= 232448, "smem");

constexpr int PAR_T1 = 0;
constexpr int PAR_T2 = 512;
constexpr int PAR_CONST = 1536;
constexpr int PAR_RED = 1600;
constexpr int PAR_SINK = 2176;

struct Maps {
  CUtensorMap x, wq, k, v, wo, wg, wu, wd, wm, out;
};
struct Ptrs {
  const __nv_bfloat16 *x, *w_r, *c, *w_mod, *w_gate, *w_up, *w_down;
  __nv_bfloat16* out;
};

__device__ __align__(1024) uint8_t g_act[16 * 80 * UNIT];
__device__ __align__(128) uint32_t g_mod[NMOD];
__device__ __align__(128) uint32_t g_modp[2 * 2 * DM];
__device__ __align__(128) uint32_t g_ln1[SEQ * 4];
__device__ __align__(128) uint32_t g_cnt_h[16 * 32];
__device__ __align__(128) uint32_t g_cnt_o[128 * 32];
__device__ __align__(128) uint32_t g_xch[NMAIN * 8 * 256 * 4];
__device__ __align__(128) uint32_t g_stats[8 * SEQ * 4];
__device__ __align__(128) uint32_t g_cand[32];
__device__ __align__(128) uint32_t g_row[16 * 2 * DM];
__device__ __align__(128) uint32_t g_ypart[NMAIN * NFFN * 8];
__device__ uint32_t g_epoch;

__device__ __forceinline__ uint32_t fresh_lane() { uint32_t l; asm volatile("mov.u32 %0, %%laneid;" : "=r"(l)); return l; }
__device__ __forceinline__ uint32_t frag_offset(int warp) {
  const uint32_t l = fresh_lane();
  return ((warp & 3) * 16 + (l & 15)) * 128 + (((l >> 4) ^ (l & 7)) << 4);
}
__device__ __forceinline__ bool elect_one() {
  uint32_t p;
  asm volatile("{ .reg .pred q; elect.sync _|q, 0xffffffff; selp.u32 %0, 1, 0, q; }" : "=r"(p));
  return p;
}
__device__ __forceinline__ uint32_t smem_u32(const void* p) { return (uint32_t)__cvta_generic_to_shared(p); }
__device__ __forceinline__ void mbar_init(uint32_t bar, uint32_t cnt) {
  asm volatile("mbarrier.init.shared::cta.b64 [%0], %1;" ::"r"(bar), "r"(cnt) : "memory");
}
__device__ __forceinline__ void mbar_expect_tx(uint32_t bar, uint32_t bytes) {
  asm volatile("mbarrier.arrive.expect_tx.shared::cta.b64 _, [%0], %1;" ::"r"(bar), "r"(bytes) : "memory");
}
__device__ __forceinline__ void mbar_arrive(uint32_t bar) {
  asm volatile("mbarrier.arrive.shared::cta.b64 _, [%0];" ::"r"(bar) : "memory");
}
__device__ __forceinline__ void mbar_arrive_pred(uint32_t bar, bool p) {
  asm volatile("{ .reg .pred p; setp.ne.b32 p, %1, 0; @p mbarrier.arrive.shared::cta.b64 _, [%0]; }" ::"r"(bar), "r"((int)p) : "memory");
}
__device__ __forceinline__ void mbar_arrive_cl(uint32_t bar, uint32_t off, bool p = true) {
  asm volatile("{ .reg .pred p, q; .reg .b32 a; setp.ne.b32 q, %2, 0; setp.ne.and.b32 p, %0, 0, q; add.u32 a, %0, %1; @p mbarrier.arrive.shared::cluster.b64 _, [a]; }"
               ::"r"(bar), "r"(off), "r"((int)p) : "memory");
}
__device__ __forceinline__ uint32_t mapa(uint32_t addr, uint32_t cta) {
  uint32_t r; asm("mapa.shared::cluster.u32 %0, %1, %2;" : "=r"(r) : "r"(addr), "r"(cta)); return r;
}
__device__ __forceinline__ void cluster_arrive() { asm volatile("barrier.cluster.arrive.relaxed.aligned;" ::: "memory"); }
__device__ __forceinline__ void cluster_wait() { asm volatile("barrier.cluster.wait.aligned;" ::: "memory"); }
__device__ __forceinline__ void watchdog(uint32_t& n) {
}
__device__ __forceinline__ void mbar_wait(uint32_t bar, uint32_t parity) {
  asm volatile("{\n.reg .pred p;\nWAIT_%=:\nmbarrier.try_wait.parity.shared::cta.b64 p, [%0], %1;\n@!p bra WAIT_%=;\n}" ::"r"(bar), "r"(parity) : "memory");
}
__device__ __forceinline__ bool mbar_test(uint32_t bar, uint32_t parity) {
  uint32_t ok;
  asm volatile("{\n.reg .pred p;\nmbarrier.test_wait.parity.shared::cta.b64 p, [%1], %2;\nselp.u32 %0, 1, 0, p;\n}" : "=r"(ok) : "r"(bar), "r"(parity) : "memory");
  return ok;
}
__device__ __forceinline__ uint64_t l2_stream() {
  uint64_t f; asm("createpolicy.fractional.L2::evict_first.b64 %0, 1.0;" : "=l"(f)); return f;
}
__device__ __forceinline__ void tma2d(uint32_t dst, const CUtensorMap* m, int c0, int c1, uint32_t bar) {
  asm volatile("cp.async.bulk.tensor.2d.shared::cluster.global.mbarrier::complete_tx::bytes.L2::cache_hint [%0], [%1, {%3, %4}], [%2], %5;"
               ::"r"(dst), "l"(m), "r"(bar), "r"(c0), "r"(c1), "l"(l2_stream()) : "memory");
}
__device__ __forceinline__ void bulk_load(uint32_t dst, const void* src, uint32_t bytes, uint32_t bar) {
  asm volatile("cp.async.bulk.shared::cluster.global.mbarrier::complete_tx::bytes [%0], [%1], %2, [%3];" ::"r"(dst), "l"(src), "r"(bytes), "r"(bar) : "memory");
}
__device__ __forceinline__ void bulk_load_stream(uint32_t dst, const void* src, uint32_t bytes, uint32_t bar) {
  asm volatile("cp.async.bulk.shared::cluster.global.mbarrier::complete_tx::bytes.L2::cache_hint [%0], [%1], %2, [%3], %4;"
               ::"r"(dst), "l"(src), "r"(bytes), "r"(bar), "l"(l2_stream()) : "memory");
}
__device__ __forceinline__ void tma2d_store(const CUtensorMap* m, uint32_t src, int c0, int c1) {
  asm volatile("cp.async.bulk.tensor.2d.global.shared::cta.bulk_group [%0, {%2, %3}], [%1];" ::"l"(m), "r"(src), "r"(c0), "r"(c1) : "memory");
}
__device__ __forceinline__ void bulk_store(void* dst, uint32_t src, uint32_t bytes) {
  asm volatile("cp.async.bulk.global.shared::cta.bulk_group [%0], [%1], %2;" ::"l"(dst), "r"(src), "r"(bytes) : "memory");
}
__device__ __forceinline__ uint32_t unit_of(uint32_t table, uint32_t i) { return ((table >> (i * 4)) & 15) * UNIT; }
__device__ __forceinline__ void tma3d(uint32_t dst, const CUtensorMap* m, int c0, int c1, int c2, uint32_t bar) {
  asm volatile("cp.async.bulk.tensor.3d.shared::cluster.global.mbarrier::complete_tx::bytes.L2::cache_hint [%0], [%1, {%3, %4, %5}], [%2], %6;"
               ::"r"(dst), "l"(m), "r"(bar), "r"(c0), "r"(c1), "r"(c2), "l"(l2_stream()) : "memory");
}
template <bool STREAM>
__device__ __forceinline__ void tma3d_mc(uint32_t dst, const CUtensorMap* m, int c0, int c1, int c2, uint32_t bar) {
  if (STREAM)
    asm volatile("cp.async.bulk.tensor.3d.shared::cluster.global.mbarrier::complete_tx::bytes.multicast::cluster.L2::cache_hint [%0], [%1, {%3, %4, %5}], [%2], %6, %7;"
                 ::"r"(dst), "l"(m), "r"(bar), "r"(c0), "r"(c1), "r"(c2), "h"((uint16_t)3), "l"(l2_stream()) : "memory");
  else
    asm volatile("cp.async.bulk.tensor.3d.shared::cluster.global.mbarrier::complete_tx::bytes.multicast::cluster [%0], [%1, {%3, %4, %5}], [%2], %6;"
                 ::"r"(dst), "l"(m), "r"(bar), "r"(c0), "r"(c1), "r"(c2), "h"((uint16_t)3) : "memory");
}
__device__ __forceinline__ void prefetch_map(const CUtensorMap* m) {
  asm volatile("prefetch.tensormap [%0];" ::"l"(m) : "memory");
}
__device__ __forceinline__ void fence_async() { asm volatile("fence.proxy.async.global;" ::: "memory"); }
__device__ __forceinline__ void fence_async_smem() { asm volatile("fence.proxy.async.shared::cta;" ::: "memory"); }
__device__ __forceinline__ void bar_sync(int id, int n) { asm volatile("bar.sync %0, %1;" ::"r"(id), "r"(n) : "memory"); }
__device__ __forceinline__ void bar_arrive(int id, int n) { asm volatile("bar.arrive %0, %1;" ::"r"(id), "r"(n) : "memory"); }
__device__ __forceinline__ void wg_fence() { asm volatile("wgmma.fence.sync.aligned;" ::: "memory"); }
__device__ __forceinline__ void wg_commit() { asm volatile("wgmma.commit_group.sync.aligned;" ::: "memory"); }
template <int N> __device__ __forceinline__ void wg_wait() { asm volatile("wgmma.wait_group.sync.aligned %0;" ::"n"(N) : "memory"); }
__device__ __forceinline__ uint64_t make_desc(uint32_t addr, uint32_t lbo, uint32_t sbo) {
  return (uint64_t)((addr & 0x3FFFF) >> 4) | ((uint64_t)(lbo >> 4) << 16) | ((uint64_t)(sbo >> 4) << 32) | (1ull << 62);
}
__device__ __forceinline__ uint32_t ld_relaxed(const uint32_t* p) {
  uint32_t v; asm volatile("ld.relaxed.gpu.global.u32 %0, [%1];" : "=r"(v) : "l"(p) : "memory"); return v;
}
__device__ __forceinline__ uint32_t ld_acquire(const uint32_t* p) {
  uint32_t v; asm volatile("ld.acquire.gpu.global.u32 %0, [%1];" : "=r"(v) : "l"(p) : "memory"); return v;
}
__device__ __forceinline__ uint4 ld_relaxed4(const uint32_t* p) {
  uint4 v; asm volatile("ld.relaxed.gpu.global.v4.u32 {%0,%1,%2,%3}, [%4];" : "=r"(v.x), "=r"(v.y), "=r"(v.z), "=r"(v.w) : "l"(p) : "memory"); return v;
}
__device__ __forceinline__ uint2 ld_relaxed2(const uint32_t* p) {
  uint2 v; asm volatile("ld.relaxed.gpu.global.v2.u32 {%0,%1}, [%2];" : "=r"(v.x), "=r"(v.y) : "l"(p) : "memory"); return v;
}
__device__ __forceinline__ void st_relaxed(uint32_t* p, uint32_t v) {
  asm volatile("st.relaxed.gpu.global.u32 [%0], %1;" ::"l"(p), "r"(v) : "memory");
}
__device__ __forceinline__ void st_relaxed2(uint32_t* p, uint32_t a, uint32_t b) {
  asm volatile("st.relaxed.gpu.global.v2.u32 [%0], {%1,%2};" ::"l"(p), "r"(a), "r"(b) : "memory");
}
__device__ __forceinline__ void st_relaxed4(uint32_t* p, uint32_t a, uint32_t b, uint32_t c, uint32_t d) {
  asm volatile("st.relaxed.gpu.global.v4.u32 [%0], {%1,%2,%3,%4};" ::"l"(p), "r"(a), "r"(b), "r"(c), "r"(d) : "memory");
}
__device__ __forceinline__ void st_b128(uint32_t* p, uint32_t a, uint32_t b, uint32_t c, uint32_t d) {
  asm volatile("{ .reg .b64 u, v; .reg .b128 w; mov.b64 u, {%1, %2}; mov.b64 v, {%3, %4}; mov.b128 w, {u, v}; st.relaxed.gpu.global.b128 [%0], w; }"
               ::"l"(p), "r"(a), "r"(b), "r"(c), "r"(d) : "memory");
}
__device__ __forceinline__ uint4 ld_b128(const uint32_t* p) {
  uint4 r;
  asm volatile("{ .reg .b64 u, v; .reg .b128 w; ld.relaxed.gpu.global.b128 w, [%4]; mov.b128 {u, v}, w; mov.b64 {%0, %1}, u; mov.b64 {%2, %3}, v; }"
               : "=r"(r.x), "=r"(r.y), "=r"(r.z), "=r"(r.w) : "l"(p) : "memory");
  return r;
}
__device__ __forceinline__ void st_pairs(uint32_t* p, uint32_t a, uint32_t b, uint32_t tag) {
  asm volatile("{ .reg .b64 u, v; mov.b64 u, {%1, %3}; mov.b64 v, {%2, %3}; st.relaxed.gpu.global.v2.b64 [%0], {u, v}; }"
               ::"l"(p), "r"(a), "r"(b), "r"(tag) : "memory");
}
__device__ __forceinline__ uint4 ld_pairs(const uint32_t* p) {
  uint4 v;
  asm volatile("{ .reg .b64 u, v; ld.relaxed.gpu.global.v2.b64 {u, v}, [%4]; mov.b64 {%0, %1}, u; mov.b64 {%2, %3}, v; }"
               : "=r"(v.x), "=r"(v.y), "=r"(v.z), "=r"(v.w) : "l"(p) : "memory");
  return v;
}
__device__ __forceinline__ uint2 ld_pair(const uint32_t* p) {
  uint2 v;
  asm volatile("{ .reg .b64 u; ld.relaxed.gpu.global.b64 u, [%2]; mov.b64 {%0, %1}, u; }" : "=r"(v.x), "=r"(v.y) : "l"(p) : "memory");
  return v;
}
__device__ __forceinline__ void red_release(uint32_t* p, uint32_t v) {
  asm volatile("red.release.gpu.global.add.u32 [%0], %1;" ::"l"(p), "r"(v) : "memory");
}
__device__ __forceinline__ uint32_t ldg_nc1(const void* p) {
  uint32_t v;
  asm volatile("ld.global.nc.u32 %0, [%1];" : "=r"(v) : "l"(p));
  return v;
}
__device__ __forceinline__ uint4 ldg_nc4(const void* p) {
  uint4 v; asm volatile("ld.global.nc.L1::no_allocate.v4.u32 {%0,%1,%2,%3}, [%4];" : "=r"(v.x), "=r"(v.y), "=r"(v.z), "=r"(v.w) : "l"(p)); return v;
}
__device__ __forceinline__ uint4 ldg_stream4(const void* p) {
  uint4 v;
  asm volatile("ld.global.nc.L1::no_allocate.L2::cache_hint.v4.u32 {%0,%1,%2,%3}, [%4], %5;" : "=r"(v.x), "=r"(v.y), "=r"(v.z), "=r"(v.w) : "l"(p), "l"(l2_stream()));
  return v;
}
__device__ __forceinline__ void stg4(void* p, uint4 v) {
  asm volatile("st.global.v4.u32 [%0], {%1,%2,%3,%4};" ::"l"(p), "r"(v.x), "r"(v.y), "r"(v.z), "r"(v.w) : "memory");
}
__device__ __forceinline__ void wait_counter(const uint32_t* p, uint32_t target) {
  uint32_t n = 0;
  while (__any_sync(0xffffffffu, (int)(ld_acquire(p) - target) < 0)) { watchdog(n); }
}
__device__ __forceinline__ uint32_t tagf(float v, uint32_t tag) { return (__float_as_uint(v) & ~3u) | tag; }
__device__ __forceinline__ bool tag_ok(uint4 v, uint32_t tag) { return (((v.x ^ tag) | (v.y ^ tag) | (v.z ^ tag) | (v.w ^ tag)) & 3u) == 0; }
__device__ __forceinline__ float untag_sum(uint32_t a, uint32_t b) { return __uint_as_float(a & ~3u) + __uint_as_float(b & ~3u); }
__device__ __forceinline__ uint4 poll4(const uint32_t* p, uint32_t tag) {
  uint4 v = ld_relaxed4(p);
  uint32_t n = 0;
  while (!__all_sync(0xffffffffu, tag_ok(v, tag))) { v = ld_relaxed4(p); watchdog(n); }
  return v;
}
__device__ __forceinline__ float bf_lo(uint32_t v) { return __uint_as_float(v << 16); }
__device__ __forceinline__ float bf_hi(uint32_t v) { return __uint_as_float(v & 0xffff0000u); }
__device__ __forceinline__ uint32_t pack_bf(float lo, float hi) {
  uint32_t r; asm("cvt.rn.bf16x2.f32 %0, %1, %2;" : "=r"(r) : "f"(hi), "f"(lo)); return r;
}
__device__ __forceinline__ float rbf(float v) { return __uint_as_float(pack_bf(0.f, v) & 0xffff0000u); }
__device__ __forceinline__ uint32_t hmul2(uint32_t a, uint32_t b) {
  uint32_t r; asm("mul.rn.bf16x2 %0, %1, %2;" : "=r"(r) : "r"(a), "r"(b)); return r;
}
__device__ __forceinline__ uint32_t hadd2(uint32_t a, uint32_t b) {
  uint32_t r; asm("add.rn.bf16x2 %0, %1, %2;" : "=r"(r) : "r"(a), "r"(b)); return r;
}
__device__ __forceinline__ uint32_t hsub2(uint32_t a, uint32_t b) {
  uint32_t r; asm("sub.rn.bf16x2 %0, %1, %2;" : "=r"(r) : "r"(a), "r"(b)); return r;
}
__device__ __forceinline__ uint32_t hmax2(uint32_t a, uint32_t b) {
  uint32_t r; asm("max.bf16x2 %0, %1, %2;" : "=r"(r) : "r"(a), "r"(b)); return r;
}
__device__ __forceinline__ float rcp(float x) { float r; asm("rcp.approx.ftz.f32 %0, %1;" : "=f"(r) : "f"(x)); return r; }
__device__ __forceinline__ float ex2(float x) { float r; asm("ex2.approx.ftz.f32 %0, %1;" : "=f"(r) : "f"(x)); return r; }
__device__ __forceinline__ void stmatrix4(uint32_t addr, uint32_t a, uint32_t b, uint32_t c, uint32_t d) {
  asm volatile("stmatrix.sync.aligned.m8n8.x4.shared.b16 [%0], {%1,%2,%3,%4};" ::"r"(addr), "r"(a), "r"(b), "r"(c), "r"(d) : "memory");
}
__device__ __forceinline__ void ldmatrix4(uint32_t addr, uint32_t& a, uint32_t& b, uint32_t& c, uint32_t& d) {
  asm volatile("ldmatrix.sync.aligned.m8n8.x4.shared.b16 {%0,%1,%2,%3}, [%4];" : "=r"(a), "=r"(b), "=r"(c), "=r"(d) : "r"(addr) : "memory");
}
__device__ __forceinline__ void ldmatrix4t(uint32_t addr, uint32_t& a, uint32_t& b, uint32_t& c, uint32_t& d) {
  asm volatile("ldmatrix.sync.aligned.m8n8.x4.trans.shared.b16 {%0,%1,%2,%3}, [%4];" : "=r"(a), "=r"(b), "=r"(c), "=r"(d) : "r"(addr) : "memory");
}
__device__ __forceinline__ void mma16816(float (&d)[4], uint32_t a0, uint32_t a1, uint32_t a2, uint32_t a3, uint32_t b0, uint32_t b1) {
  asm volatile("mma.sync.aligned.m16n8k16.row.col.f32.bf16.bf16.f32 {%0,%1,%2,%3}, {%4,%5,%6,%7}, {%8,%9}, {%0,%1,%2,%3};"
               : "+f"(d[0]), "+f"(d[1]), "+f"(d[2]), "+f"(d[3]) : "r"(a0), "r"(a1), "r"(a2), "r"(a3), "r"(b0), "r"(b1));
}
__device__ __forceinline__ void sts1(uint32_t a, uint32_t v) { asm volatile("st.shared.u32 [%0], %1;" ::"r"(a), "r"(v) : "memory"); }
__device__ __forceinline__ uint4 lds4(uint32_t a) {
  uint4 v; asm volatile("ld.shared.v4.u32 {%0,%1,%2,%3}, [%4];" : "=r"(v.x), "=r"(v.y), "=r"(v.z), "=r"(v.w) : "r"(a) : "memory"); return v;
}
__device__ __forceinline__ uint2 lds2(uint32_t a) {
  uint2 v; asm volatile("ld.shared.v2.u32 {%0,%1}, [%2];" : "=r"(v.x), "=r"(v.y) : "r"(a) : "memory"); return v;
}
__device__ __forceinline__ uint32_t lds1(uint32_t a) {
  uint32_t v; asm volatile("ld.shared.u32 %0, [%1];" : "=r"(v) : "r"(a) : "memory"); return v;
}
__device__ __forceinline__ void sts2(uint32_t a, uint32_t x, uint32_t y) { asm volatile("st.shared.v2.u32 [%0], {%1,%2};" ::"r"(a), "r"(x), "r"(y) : "memory"); }
__device__ __forceinline__ void sts4(uint32_t a, uint4 v) {
  asm volatile("st.shared.v4.u32 [%0], {%1,%2,%3,%4};" ::"r"(a), "r"(v.x), "r"(v.y), "r"(v.z), "r"(v.w) : "memory");
}
__device__ __forceinline__ float silu_f(float v) { return __fdividef(v, 1.f + __expf(-v)); }
__device__ __forceinline__ uint32_t hfma2(uint32_t a, uint32_t b, uint32_t c) {
  uint32_t r; asm("fma.rn.bf16x2 %0, %1, %2, %3;" : "=r"(r) : "r"(a), "r"(b), "r"(c)); return r;
}
__device__ __forceinline__ void split_inv(float sd, uint32_t& ih, uint32_t& il) {
  const float inv = rcp(sd);
  ih = pack_bf(inv, inv);
  const float lo = inv - bf_lo(ih);
  il = pack_bf(lo, lo);
}
__device__ __forceinline__ uint32_t ln_norm(uint32_t x, uint32_t mean2, uint32_t ih, uint32_t il) {
  const uint32_t d = hsub2(x, mean2);
  return hfma2(d, ih, hmul2(d, il));
}
__device__ __forceinline__ uint32_t modul(uint32_t n, uint32_t c1, uint32_t sh) { return hadd2(hmul2(n, c1), sh); }
__device__ __forceinline__ uint32_t ln_mod(uint32_t x, uint32_t mean2, uint32_t ih, uint32_t il, uint32_t c1, uint32_t sh) {
  return modul(ln_norm(x, mean2, ih, il), c1, sh);
}

#define R8(a, i) "+f"(a[i]), "+f"(a[i + 1]), "+f"(a[i + 2]), "+f"(a[i + 3]), "+f"(a[i + 4]), "+f"(a[i + 5]), "+f"(a[i + 6]), "+f"(a[i + 7])
#define D64 "{%0,%1,%2,%3,%4,%5,%6,%7,%8,%9,%10,%11,%12,%13,%14,%15,%16,%17,%18,%19,%20,%21,%22,%23,%24,%25,%26,%27,%28,%29,%30,%31," \
            "%32,%33,%34,%35,%36,%37,%38,%39,%40,%41,%42,%43,%44,%45,%46,%47,%48,%49,%50,%51,%52,%53,%54,%55,%56,%57,%58,%59,%60,%61,%62,%63}"
template <int TB>
__device__ __forceinline__ void mma_ss(float (&d)[64], uint64_t da, uint64_t db, int sc) {
  asm volatile("{\n.reg .pred p;\nsetp.ne.b32 p, %66, 0;\n"
               "wgmma.mma_async.sync.aligned.m64n128k16.f32.bf16.bf16 " D64 ", %64, %65, p, 1, 1, 0, %67;\n}"
               : R8(d, 0), R8(d, 8), R8(d, 16), R8(d, 24), R8(d, 32), R8(d, 40), R8(d, 48), R8(d, 56)
               : "l"(da), "l"(db), "r"(sc), "n"(TB));
}
template <int TB>
__device__ __forceinline__ void mma_rs(float (&d)[64], uint32_t a0, uint32_t a1, uint32_t a2, uint32_t a3, uint64_t db, int sc) {
  asm volatile("{\n.reg .pred p;\nsetp.ne.b32 p, %69, 0;\n"
               "wgmma.mma_async.sync.aligned.m64n128k16.f32.bf16.bf16 " D64 ", {%64,%65,%66,%67}, %68, p, 1, 1, %70;\n}"
               : R8(d, 0), R8(d, 8), R8(d, 16), R8(d, 24), R8(d, 32), R8(d, 40), R8(d, 48), R8(d, 56)
               : "r"(a0), "r"(a1), "r"(a2), "r"(a3), "l"(db), "r"(sc), "n"(TB));
}
#define D128 "{%0,%1,%2,%3,%4,%5,%6,%7,%8,%9,%10,%11,%12,%13,%14,%15,%16,%17,%18,%19,%20,%21,%22,%23,%24,%25,%26,%27,%28,%29,%30,%31," \
             "%32,%33,%34,%35,%36,%37,%38,%39,%40,%41,%42,%43,%44,%45,%46,%47,%48,%49,%50,%51,%52,%53,%54,%55,%56,%57,%58,%59,%60,%61,%62,%63," \
             "%64,%65,%66,%67,%68,%69,%70,%71,%72,%73,%74,%75,%76,%77,%78,%79,%80,%81,%82,%83,%84,%85,%86,%87,%88,%89,%90,%91,%92,%93,%94,%95," \
             "%96,%97,%98,%99,%100,%101,%102,%103,%104,%105,%106,%107,%108,%109,%110,%111,%112,%113,%114,%115,%116,%117,%118,%119,%120,%121,%122,%123,%124,%125,%126,%127}"
#define R128(d, e) R8(d, 0), R8(d, 8), R8(d, 16), R8(d, 24), R8(d, 32), R8(d, 40), R8(d, 48), R8(d, 56), \
                   R8(e, 0), R8(e, 8), R8(e, 16), R8(e, 24), R8(e, 32), R8(e, 40), R8(e, 48), R8(e, 56)
__device__ __forceinline__ void mma256_ss(float (&d)[64], float (&e)[64], uint64_t da, uint64_t db, int sc) {
  asm volatile("{\n.reg .pred p;\nsetp.ne.b32 p, %130, 0;\n"
               "wgmma.mma_async.sync.aligned.m64n256k16.f32.bf16.bf16 " D128 ", %128, %129, p, 1, 1, 0, 1;\n}"
               : R128(d, e) : "l"(da), "l"(db), "r"(sc));
}
__device__ __forceinline__ void mma256_rs(float (&d)[64], float (&e)[64], uint32_t a0, uint32_t a1, uint32_t a2, uint32_t a3, uint64_t db) {
  asm volatile("{\n.reg .pred p;\nsetp.ne.b32 p, 1, 0;\n"
               "wgmma.mma_async.sync.aligned.m64n256k16.f32.bf16.bf16 " D128 ", {%128,%129,%130,%131}, %132, p, 1, 1, 1;\n}"
               : R128(d, e) : "r"(a0), "r"(a1), "r"(a2), "r"(a3), "l"(db));
}
template <int N> __device__ __forceinline__ void keep(float (&a)[N]) {
#pragma unroll
  for (int i = 0; i < N; i++) asm volatile("" : "+f"(a[i])::"memory");
}
template <int N> __device__ __forceinline__ void keep(uint32_t (&a)[N]) {
#pragma unroll
  for (int i = 0; i < N; i++) asm volatile("" : "+r"(a[i])::"memory");
}

#define STAMP(idx) do {} while (0)
#define PROF(grp, cond, idx) do {} while (0)

constexpr float SCL2 = 1.4426950408889634f * 0.08838834764831845f;

__device__ __forceinline__ void pack_p(const float (&s)[64], uint32_t (&p)[32]) {
#pragma unroll
  for (int i = 0; i < 32; i++) p[i] = pack_bf(s[2 * i], s[2 * i + 1]);
}

__device__ __forceinline__ void issue_qk(float (&s)[64], uint32_t q0, uint32_t q1, uint32_t kslot) {
  const uint64_t db = make_desc(kslot, 16, 1024), da0 = make_desc(q0, 16, 1024), da1 = make_desc(q1, 16, 1024);
#pragma unroll
  for (int kk = 0; kk < 8; kk++) mma_ss<0>(s, (kk < 4 ? da0 : da1) + (kk & 3) * 2, db + (kk >> 2) * 1024 + (kk & 3) * 2, kk != 0);
}
__device__ __forceinline__ void issue_pv(float (&o)[64], uint32_t (&p)[32], uint32_t vslot, int acc) {
  uint64_t db = make_desc(vslot, 16384, 1024);
#pragma unroll
  for (int kk = 0; kk < 8; kk++)
    mma_rs<1>(o, p[4 * kk], p[4 * kk + 1], p[4 * kk + 2], p[4 * kk + 3], db + kk * 128, kk == 0 ? acc : 1);
}

template <int H>
__device__ __forceinline__ void store_chunk(const float (&a)[64], uint32_t addr) {
#pragma unroll
  for (int i = 8 * H; i < 8 * H + 8; i += 2)
    stmatrix4(addr ^ ((i & 7) << 4), pack_bf(a[4 * i], a[4 * i + 1]), pack_bf(a[4 * i + 2], a[4 * i + 3]),
              pack_bf(a[4 * i + 4], a[4 * i + 5]), pack_bf(a[4 * i + 6], a[4 * i + 7]));
}
template <int H>
__device__ __forceinline__ void store_chunk(const float (&a)[64], float i0, float i1, uint32_t addr) {
#pragma unroll
  for (int i = 8 * H; i < 8 * H + 8; i += 2)
    stmatrix4(addr ^ ((i & 7) << 4), pack_bf(a[4 * i] * i0, a[4 * i + 1] * i0), pack_bf(a[4 * i + 2] * i1, a[4 * i + 3] * i1),
              pack_bf(a[4 * i + 4] * i0, a[4 * i + 5] * i0), pack_bf(a[4 * i + 6] * i1, a[4 * i + 7] * i1));
}
__device__ __forceinline__ float inv_quad_sum(float l) {
  l += __shfl_xor_sync(0xffffffffu, l, 1);
  l += __shfl_xor_sync(0xffffffffu, l, 2);
  return rcp(l);
}

__device__ __forceinline__ void ln_scalars(float mean, float var, float& mb, float& sd) {
  mb = rbf(mean);
  float r; asm("sqrt.approx.ftz.f32 %0, %1;" : "=f"(r) : "f"(rbf(rbf(var) + 1e-5f)));
  sd = rbf(r);
}

__global__ void __cluster_dims__(2, 1, 1) __launch_bounds__(384, 1) fused_kernel(const __grid_constant__ Maps maps, const Ptrs P) {
  extern __shared__ __align__(1024) uint8_t smem_raw[];
  const uint32_t base = smem_u32(smem_raw);
  const int tid = threadIdx.x, lane = tid & 31;
  const int warp = __shfl_sync(0xffffffffu, tid >> 5, 0);
  const int b = blockIdx.x;
  PROF(31, tid == 0, 0);

  if (b >= NMAIN) {
    float* sc = reinterpret_cast<float*>(smem_raw);
    float* red = sc + DM;
    for (int k = tid; k < DM; k += 384) sc[k] = rbf(silu_f(__bfloat162float(P.c[k])));
    __syncthreads();
    if (tid < 256) {
      const int col = 2048 + (b - NMAIN) * 1024 + (tid & 127) * 8, r0 = (tid >> 7) * 512;
      float acc[8];
#pragma unroll
      for (int e = 0; e < 8; e++) acc[e] = 0.f;
#pragma unroll 1
      for (int r = r0; r < r0 + 512; r += HU) {
        uint4 w[HU];
#pragma unroll
        for (int u = 0; u < HU; u++) w[u] = ldg_stream4(P.w_mod + (size_t)(r + u) * NMOD + col);
#pragma unroll
        for (int u = 0; u < HU; u++) {
          float s = sc[r + u];
          acc[0] += s * bf_lo(w[u].x); acc[1] += s * bf_hi(w[u].x); acc[2] += s * bf_lo(w[u].y); acc[3] += s * bf_hi(w[u].y);
          acc[4] += s * bf_lo(w[u].z); acc[5] += s * bf_hi(w[u].z); acc[6] += s * bf_lo(w[u].w); acc[7] += s * bf_hi(w[u].w);
        }
      }
      if (tid >= 128) {
#pragma unroll
        for (int e = 0; e < 8; e++) red[(tid & 127) * 8 + e] = acc[e];
      }
      const uint32_t tag = ld_relaxed(&g_epoch) % 3 + 1;
      bar_sync(1, 256);
      if (tid < 128) {
        uint32_t o[8];
#pragma unroll
        for (int e = 0; e < 8; e++) o[e] = __float_as_uint(rbf(acc[e] + red[tid * 8 + e])) | tag;
        st_relaxed4(g_mod + col, o[0], o[1], o[2], o[3]);
        st_relaxed4(g_mod + col + 4, o[4], o[5], o[6], o[7]);
        const uint4 wr = ldg_nc4(P.w_r + tid * 8);
        const uint32_t wv[4] = {wr.x, wr.y, wr.z, wr.w};
        float dsum = 0.f;
#pragma unroll
        for (int e = 0; e < 8; e++) {
          const float m = bf_hi(o[e]);
          dsum += (b == NMAIN + 2 ? rbf(1.f + m) : m) * ((e & 1) ? bf_hi(wv[e >> 1]) : bf_lo(wv[e >> 1]));
        }
#pragma unroll
        for (int k = 16; k > 0; k >>= 1) dsum += __shfl_xor_sync(0xffffffffu, dsum, k);
        if (lane == 0) st_relaxed(g_mod + (b - NMAIN) * 4 + warp, tagf(dsum, tag));
      }
    }
    PROF(2, tid == 0, 1);
    return;
  }

  const int rank = b & 1;
  const int rb = ((b >> 4) << 1) | rank, cj = (b >> 1) & 7;
  const uint32_t bfull = base + OFF_BAR, bempty = bfull + NSLOT * 8;
  const uint32_t gfull = bempty + NSLOT * 8, gempty = gfull + 32;
  const uint32_t bar_ofull = gempty + 32;
  const uint32_t bar_ofree = bar_ofull + 32;
  const uint32_t bar_par = bar_ofree + 32;
  const uint32_t bar_mod = bar_par + 8;
  const uint32_t bar_pread = bar_mod + 8;
  const uint32_t bar_xres = bar_pread + 8;
  const uint32_t bar_ring = bar_xres + 8;
  const uint32_t bar_box = bar_ring + 24;
  const uint32_t bar_go = bar_box + 96;
  const uint32_t bar_go2 = bar_go + 16;
  const uint32_t bar_cnt = bar_go + 24;
  const uint32_t xfull = bar_go + 40, xempty = xfull + 32;
  const uint32_t bar_hw = xempty + 32, bar_hx = bar_hw + 8;
  const uint32_t bar_hpub = bar_hx + 16;
  const uint32_t bar_win = bar_hpub + 16;
  const uint32_t bar_rx = bar_win + 8;
  const uint32_t bar_sel = bar_rx + 8;
  const uint32_t bar_gate = bar_sel + 8;
  const uint32_t bar_rel = bar_gate + 8;
  const uint32_t bar_od = bar_rel + 8;
  const uint32_t bar_res = bar_go + 8;
  const uint32_t stage = base + OFF_STAGE, par = base + OFF_PAR;

  if (warp == 8 && elect_one()) {
    for (int s = 0; s < NSLOT; s++) { mbar_init(bfull + s * 8, 1); mbar_init(bempty + s * 8, 16); }
    for (int s = 0; s < 4; s++) { mbar_init(gfull + s * 8, 1); mbar_init(gempty + s * 8, 16); mbar_init(xfull + s * 8, 1); mbar_init(xempty + s * 8, 8); mbar_init(bar_ofree + s * 8, 1); mbar_init(bar_ofull + s * 8, 128); }
    mbar_init(bar_par, 64); mbar_init(bar_mod, 256); mbar_init(bar_pread, 2); mbar_init(bar_xres, 1);
    mbar_init(bar_ring, 8); mbar_init(bar_ring + 8, 8); mbar_init(bar_ring + 16, 8);
    mbar_init(bar_go, 1); mbar_init(bar_go2, 1); mbar_init(bar_cnt, 1); mbar_init(bar_cnt + 8, 1); mbar_init(bar_hpub, 8); mbar_init(bar_hpub + 8, 8); mbar_init(bar_res, 1); mbar_init(bar_win, 1); mbar_init(bar_rx, 1); mbar_init(bar_sel, 64); mbar_init(bar_gate, 8); mbar_init(bar_rel, 8); mbar_init(bar_od, 1);
    for (int s = 0; s < 12; s++) mbar_init(bar_box + s * 8, 1);
    asm volatile("fence.mbarrier_init.release.cluster;" ::: "memory");
    prefetch_map(&maps.x); prefetch_map(&maps.wq); prefetch_map(&maps.k); prefetch_map(&maps.v);
  }
  if (warp == 9 && elect_one()) {
    mbar_init(bar_hw, 1); mbar_init(bar_hx, 1); mbar_init(bar_hx + 8, 1);
    asm volatile("fence.mbarrier_init.release.cluster;" ::: "memory");
    mbar_expect_tx(bar_hw, 32768);
    mbar_expect_tx(bar_hx, 16384);
    mbar_expect_tx(bar_hx + 8, 16384);
    const __nv_bfloat16* xs = P.x + (size_t)(rb * 128 + cj * 16) * DM;
    bulk_load(base + 2 * GST_BYTES, xs, 16384, bar_hx);
    tma2d(stage, &maps.wm, (b >> 1) * 32, rank * 512, bar_hw);
    tma2d(stage + 16384, &maps.wm, (b >> 1) * 32, rank * 512 + 256, bar_hw);
    bulk_load(base + 3 * GST_BYTES, xs + 8 * DM, 16384, bar_hx + 8);
  }
  cluster_arrive();

  if (warp >= 8) {
    asm volatile("setmaxnreg.dec.sync.aligned.u32 40;");
    if (warp < 10) bar_arrive(1, 320);
    const uint32_t epoch = ld_relaxed(&g_epoch);
    cluster_wait();
    if (warp == 8) {
      const int kvrow = (cj >> 1) * SK + (SK - WIN);
      int wch = cj * 8 + rank * 2;
#pragma unroll 1
      for (int ps = 0; ps < 3; ps++) {
        const CUtensorMap* mw = ps == 2 ? &maps.wo : &maps.wq;
        const uint32_t xt = ps == 1 ? XT1 : XT2, wt = ps == 0 ? WT0 : (ps == 1 ? WT1 : WT2);
        const int nst = ps == 2 ? 32 : 16;
#pragma unroll 1
        for (int i = 0; i < nst; i++) {
          const uint32_t bf = gfull + (i & 3) * 8;
          const int kt = ps == 2 ? (((cj & 1) * 4 + ((i >> 1) & 3)) * 4 + (i >> 3)) * 2 + (i & 1) : (i + (ps ? 0 : b & 14)) & 15;
          const uint32_t wd = base + unit_of(wt, i & 3) + rank * UNIT, xd = base + unit_of(xt, i & 3);
          const uint8_t* xs = g_act + (uint32_t)(rb * 80 + (ps - 1) * 16 + kt) * UNIT;
          if (ps == 0 && i == HD) mbar_wait(bar_mod, 0);
          const bool xfirst = ps && i < 2;
          if (ps == 2 && i == 0) mbar_wait(bar_ofree + 24, 0);
          if (i == 0) fence_async();
          mbar_wait(gempty + (i & 3) * 8, ((i >> 2) & 1) ^ 1);
          if (elect_one()) {
            mbar_expect_tx(bf, ps ? GST_BYTES : 2 * UNIT);
            if (xfirst) bulk_load_stream(xd, xs, UNIT, bf);
          }
          if (ps && i < 4) mbar_wait(bempty + i * 8, 1);
          if (elect_one()) tma3d_mc<true>(wd, mw, 0, (i == 31 ? kt ^ (rank * 32) : kt) * 64, i == 31 ? cj * 2 : wch, bf);
          if (ps) {
            if (i == 16 || i == 24) { mbar_wait(bar_cnt + i - 16, 0); fence_async(); }
            if (i == RES0) mbar_wait(bar_res, 0);
            if (i == 2) mbar_wait(bar_ofree + (ps - 1) * 16, 0);
            if (elect_one()) {
              if (i == 31) bulk_load(xd, xs, UNIT, bf); else if (!xfirst) bulk_load_stream(xd, xs, UNIT, bf);
              mbar_arrive_pred(bar_go, i == GOST - 1);
              mbar_arrive_pred(bar_od, i == ODS);
              if (i == RES0) mbar_expect_tx(bar_xres, 32768);
              if (i == RES0 || i == RES1) tma2d(base + OFF_RES + (i == RES1) * UNIT, &maps.x, cj * 128 + (i == RES1) * 64, rb * 128, bar_xres);
            }
          }
        }
        if (ps == 2) break;
        wch = ps ? ((wch >> 3) ^ rank) * 2 : wch + 4;
#pragma unroll 1
        for (int u = 0; u < 16; u++) {
          const bool isk = (u == 0) || ((u & 1) && u < 15);
          const int blk = (isk ? (u + 1) >> 1 : (u == 15 ? 7 : (u >> 1) - 1)) & 3;
          const uint32_t sl = base + unit_of(ps ? AT1 : AT0, u & 3) + rank * UNIT, bf = bfull + (u & 3) * 8;
          if (u < 4) mbar_wait(gempty + ((u + 1) >> 1) * 8, 1);
          mbar_wait(bempty + (u & 3) * 8, ((u >> 2) & 1) ^ 1);
          if (elect_one()) {
            mbar_arrive_pred(bar_go2, ps && u == PG0);
            mbar_expect_tx(bf, SLOT_BYTES);
            tma3d_mc<false>(sl, isk ? &maps.k : &maps.v, 0, kvrow + blk * 128, rank, bf);
          }
        }
      }
      if (elect_one()) mbar_expect_tx(bar_rx, UNIT);
      mbar_wait(bar_rel, 0);
      if (elect_one()) {
        bulk_load_stream(base + UNIT, g_act + (uint32_t)(rb * 80 + 16 + 63 - (cj & 1) * 32) * UNIT, UNIT, bar_rx);
      }
      if (b < NFFN) {
#pragma unroll 1
        for (int u = 0; u < 12; u++) {
          const uint32_t dst = base + unit_of(u < 4 ? FT_G : (u < 8 ? FT_U : FT_D), u & 3);
          if (elect_one()) mbar_expect_tx(bar_box + u * 8, UNIT);
          if (u == FB0 || u == 2 || u == FB2) mbar_wait(bar_ring + (u == FB2 ? 16 : (u + 6) & 8), 0);
          if (u >= FPACE) mbar_wait(bar_box + (u - FPACE) * 8, 0);
          if (elect_one()) {
            if (u < 8) tma2d(dst, u < 4 ? &maps.wg : &maps.wu, b * 32, (u & 3) * 256, bar_box + u * 8);
            else tma3d(dst, &maps.wd, 0, b * 32, (u - 8) * 4, bar_box + u * 8);
          }
        }
      }
    } else if (warp == 9) {
      const uint32_t target = 8 * (epoch + 1);
      uint32_t hmask = 0;
#pragma unroll 1
      for (int i = 0; i < 16; i++) {
        if (i == HDX) mbar_wait(bar_mod, 0);
        const uint32_t need = i == 15 ? 0xffffu : 1u << ((2 * cj + i) & 15);
        if (i >= NRS && (hmask & need) != need) {
          uint32_t n = 0;
          do { hmask = __ballot_sync(0xffffffffu, ld_acquire(&g_cnt_h[rb * 32 + (lane & 15)]) == epoch + 1); watchdog(n); } while ((hmask & need) != need);
          PROF(1, lane == 0 && i == NRS, 26);
          fence_async();
        }
        mbar_wait(xempty + (i & 3) * 8, ((i >> 2) & 1) ^ 1);
        if (elect_one()) {
          mbar_expect_tx(xfull + (i & 3) * 8, UNIT);
          if (i < NRS) tma2d(base + (i & 3) * GST_BYTES, &maps.x, ((2 * cj + i) & 15) * 64, rb * 128, xfull + (i & 3) * 8);
          else bulk_load_stream(base + (i & 3) * GST_BYTES, g_act + (uint32_t)(rb * 80 + ((2 * cj + i) & 15)) * UNIT, UNIT, xfull + (i & 3) * 8);
        }
      }
      prefetch_map(&maps.wo);
#pragma unroll 1
      for (int t = 0; t < 4; t++) {
        if (t & 1) mbar_wait(bar_od, t >> 1);
#pragma unroll 1
        for (int p = 0; p < 32768 / OPS; p++) {
          const uint32_t w = p / (16384 / OPS), c = (p / (8192 / OPS)) & 1, off = w * 8192 + (p % (8192 / OPS)) * OPS;
          mbar_wait(bar_ofull + (t & 1) * 16 + w * 8, t >> 1);
          if (elect_one()) {
            bulk_store(g_act + (uint32_t)(rb * 80 + 16 + (cj * 4 + t) * 2 + c) * UNIT + off, base + unit_of(QT, 2 * t + c) + off, OPS);
            asm volatile("cp.async.bulk.commit_group;" ::: "memory");
            asm volatile("cp.async.bulk.wait_group.read %0;" ::"n"(OFL) : "memory");
          }
        }
        if (elect_one()) {
          asm volatile("cp.async.bulk.wait_group.read 0;" ::: "memory");
          mbar_arrive(t < 3 ? bar_ofree + t * 8 : bar_res);
          asm volatile("cp.async.bulk.wait_group 0;" ::: "memory");
          fence_async();
          red_release(&g_cnt_o[((rb * 4 + t) * 2 + (cj >> 2)) * 32], 2);
        }
        if (t) {
          wait_counter(&g_cnt_o[(rb * 8 + 2 * t + (cj & 1)) * 32], target);
          if (t & 1) wait_counter(&g_cnt_o[(rb * 8 + (t == 1 ? cj & 1 : 7 - (cj & 1))) * 32], target);
          if (elect_one()) mbar_arrive(t == 1 ? bar_ofree + 24 : bar_cnt + t * 8 - 16);
        }
      }
      PROF(2, lane == 0, 27);
      const uint32_t tag = epoch % 3 + 1;
      const uint32_t* inbox = g_cand + (lane & 15);
      mbar_wait(bar_ring + 16, 0);
      uint32_t c0 = ld_relaxed(inbox), n = 0;
#define CAND_STEP(cv)                                                                                        \
      {                                                                                                      \
        const bool valid = (cv & 3u) == tag, all = __all_sync(0xffffffffu, valid);                           \
        const uint32_t best = __reduce_max_sync(0xffffffffu, valid ? cv : 0u);                               \
        const uint32_t blk = __ffs(__ballot_sync(0xffffffffu, cv == best)) - 1;                              \
        if (best) sts2(par + PAR_CONST + 56, best, (blk << 7 | (~best >> 2 & 127)) | (all ? 0x1800 : 0x800)); \
        if (all) break;                                                                                      \
        cv = ld_relaxed(inbox);                                                                              \
      }
      while (true) { CAND_STEP(c0) watchdog(n); }
    } else {
      const int t2 = tid - 320;
      mbar_wait(bar_hpub + (warp & 1) * 8, 0);
      PROF(1, t2 == 0, 24);
#pragma unroll 1
      for (int c = 0; c < 8; c++) {
        const uint32_t off = (warp & 1) * UNIT + c * 2048 + lane * 16;
        uint8_t* dst = g_act + (uint32_t)(rb * 80 + cj * 2) * UNIT + off;
        const uint4 v0 = lds4(stage + off), v1 = lds4(stage + off + 512), v2 = lds4(stage + off + 1024), v3 = lds4(stage + off + 1536);
        stg4(dst, v0); stg4(dst + 512, v1); stg4(dst + 1024, v2); stg4(dst + 1536, v3);
      }
      __syncwarp();
      PROF(1, t2 == 0, 15);
      if (lane == 0) {
        mbar_arrive(bar_pread);
        red_release(&g_cnt_h[rb * 32 + cj * 2 + (warp & 1)], 1);
        PROF(1, t2 == 0, 25);
        prefetch_map(&maps.wg); prefetch_map(&maps.wu); prefetch_map(&maps.wd); prefetch_map(&maps.out);
      }
      __syncwarp();
      if (b < NFFN) {
        mbar_wait(bar_go2, 0);
        const __nv_bfloat16* pg = ((b & 1) ? P.w_up : P.w_gate) + (b >> 1) * 64 + (size_t)t2 * FF;
        const __nv_bfloat16* pd = P.w_down + (size_t)b * 32768 + t2 * 64;
        PROF(2, t2 == 0, 13);
#pragma unroll 1
        for (int i = 0; i < WN; i += WB) {
          uint32_t v[WB];
#pragma unroll
          for (int u = 0; u < WB; u++) {
            const int k = i + u;
            asm volatile("ld.global.cg.L2::128B.u32 %0, [%1];" : "=r"(v[u]) : "l"(k < 16 ? pg + (size_t)k * 64 * FF : pd + (k - 16) * 4096));
          }
#pragma unroll
          for (int u = 1; u < WB; u++) v[0] ^= v[u];
          sts1(par + PAR_SINK + t2 * 4, v[0]);
        }
        PROF(2, t2 == 0, 14);
      }
      const uint32_t tag = epoch % 3 + 1;
      mbar_wait(bar_go, 0);
      if (warp == 10) {
        const uint32_t* src = g_mod + 2 * DM + cj * 128 + lane * 4;
        const uint2 wr = *reinterpret_cast<const uint2*>(P.w_r + cj * 128 + lane * 4);
        uint4 vga, vsb, vcb, vgb;
        uint32_t n = 0;
        do {
          vga = ld_relaxed4(src); vsb = ld_relaxed4(src + DM); vcb = ld_relaxed4(src + 2 * DM); vgb = ld_relaxed4(src + 3 * DM);
          watchdog(n);
        } while (!__all_sync(0xffffffffu, tag_ok(vga, tag) && tag_ok(vsb, tag) && tag_ok(vcb, tag) && tag_ok(vgb, tag)));
        const float c0 = rbf(1.f + bf_hi(vcb.x)), c1 = rbf(1.f + bf_hi(vcb.y)), c2 = rbf(1.f + bf_hi(vcb.z)), c3 = rbf(1.f + bf_hi(vcb.w));
        const float a0 = c0 * bf_lo(wr.x), a1 = c1 * bf_hi(wr.x), a2 = c2 * bf_lo(wr.y), a3 = c3 * bf_hi(wr.y);
        const uint32_t h0 = pack_bf(a0, a1), h1 = pack_bf(a2, a3);
        const uint32_t t1 = par + PAR_T1 + (lane >> 2) * 64 + (lane & 1) * 32 + (lane & 2) * 2;
        sts1(t1, h0); sts1(t1 + 8, pack_bf(a0 - bf_lo(h0), a1 - bf_hi(h0)));
        sts1(t1 + 16, h1); sts1(t1 + 24, pack_bf(a2 - bf_lo(h1), a3 - bf_hi(h1)));
        sts4(par + PAR_T2 + lane * 32, make_uint4(pack_bf(c0, c1), __byte_perm(vsb.x, vsb.y, 0x7632), __byte_perm(vgb.x, vgb.y, 0x7632), __byte_perm(vga.x, vga.y, 0x7632)));
        sts4(par + PAR_T2 + lane * 32 + 16, make_uint4(pack_bf(c2, c3), __byte_perm(vsb.z, vsb.w, 0x7632), __byte_perm(vgb.z, vgb.w, 0x7632), __byte_perm(vga.z, vga.w, 0x7632)));
      } else {
        const uint4 g = poll4((lane & 2) ? g_mod + 8 - (lane & 1) * 4 : g_mod + 5 * DM + b * 8 + (lane & 1) * 4, tag);
        sts1(par + PAR_CONST + 60, 0);
        if (lane < 2) sts4(par + PAR_CONST + 16 + lane * 16, g);
        else if (lane < 4) sts2(par + PAR_CONST + (lane - 2) * 8, __float_as_uint(untag_sum(g.x, g.y) + untag_sum(g.z, g.w)), epoch);
      }
      __syncwarp();
#pragma unroll 4
      for (int q = XR; q < XE; q++) st_b128(g_xch + ((size_t)b * 8 * 256 + q * 64 + t2) * 4, (epoch & 1) << 16, 0, 0, 0);
      for (int q = 0; q < 2; q++) st_relaxed4(g_stats + ((size_t)cj * SEQ + rb * 128 + q * 64 + t2) * 4, 0, 0, 0, 0);
      if (b < NFFN)
        for (int q = 0; q < 4; q++) st_relaxed4(g_ypart + ((size_t)(q * 32 + (t2 >> 1)) * NFFN + b) * 8 + (t2 & 1) * 4, 0, 0, 0, 0);
      st_relaxed4(g_row + rb * 2 * DM + (t2 >> 5) * DM + cj * 128 + (t2 & 31) * 4, 0, 0, 0, 0);
      __threadfence();
      mbar_arrive(bar_par);
      mbar_wait(bar_gate, 0);
      uint32_t have = 0, n = 0;
      while (true) {
        const uint32_t st = lds1(par + PAR_CONST + 60) >> 7;
        if ((st & 31) != have) {
          const uint32_t* hsrc = g_row + (st & 15) * 2 * DM + t2 * 4;
          uint4 hv[4];
          bool ok = true;
#pragma unroll
          for (int i = 0; i < 4; i++) hv[i] = ld_pairs(hsrc + i * 256);
#pragma unroll
          for (int i = 0; i < 4; i++) {
            sts2(base + ((FT_G >> i * 4) & 15) * UNIT + (warp & 1) * 8192 + 256 + lane * 8, hv[i].x, hv[i].z);
            ok = ok && hv[i].y == tag && hv[i].w == tag;
          }
          have = __all_sync(0xffffffffu, ok) ? st & 31 : 0;
        }
        if ((st ^ have) == 32) break;
        watchdog(n);
      }
      mbar_arrive(bar_sel);
    }
    __syncwarp();
    cluster_arrive();
    {
      const uint32_t tag = epoch % 3 + 1, t3 = tid - 256;
      mbar_wait(bar_win, 0);
      uint2 win = lds2(par + PAR_CONST + 56);
      win.y &= 0x7ff;
      const uint32_t* fsrc = g_row + (win.y >> 7) * 2 * DM + (b >> 1) * 16 + (t3 & 3) * 4 + (b & 1) * 2;
      const uint32_t* ysrc = g_ypart + (size_t)b * NFFN * 8 + min(t3, NFFN - 1) * 4;
      uint2 fh = ld_pair(fsrc), fx = ld_pair(fsrc + DM);
      if (PSL) __nanosleep(PSL);
      uint4 ya = ld_relaxed4(ysrc), yb = ld_relaxed4(ysrc + NFFN * 4);
      const float rwin = __uint_as_float(((int)win.x < 0 ? win.x & 0x7fffffffu : ~win.x) & ~0x1ffu);
      const float rs = rbf(rcp(1.f + __expf(-rbf(rwin))));
      uint32_t n = 0;
      while (__any_sync(0xffffffffu, fh.y != tag || fx.y != tag)) { fh = ld_pair(fsrc); fx = ld_pair(fsrc + DM); watchdog(n); }
      while (!__all_sync(0xffffffffu, tag_ok(ya, tag) && tag_ok(yb, tag))) {
        if (!tag_ok(ya, tag)) ya = ld_relaxed4(ysrc);
        if (!tag_ok(yb, tag)) yb = ld_relaxed4(ysrc + NFFN * 4);
        watchdog(n);
      }
      __syncwarp();
      PROF(8, t3 == 0, 5);
      float y0 = untag_sum(ya.x, yb.x), y1 = untag_sum(ya.y, yb.y), y2 = untag_sum(ya.z, yb.z), y3 = untag_sum(ya.w, yb.w);
      const bool u1 = lane & 2, u2 = lane & 4;
      y0 = (u1 ? y2 : y0) + __shfl_xor_sync(0xffffffffu, u1 ? y0 : y2, 2);
      y1 = (u1 ? y3 : y1) + __shfl_xor_sync(0xffffffffu, u1 ? y1 : y3, 2);
      y0 = (u2 ? y1 : y0) + __shfl_xor_sync(0xffffffffu, u2 ? y0 : y1, 4);
      y0 += __shfl_xor_sync(0xffffffffu, y0, 8);
      if (!(lane & 8)) sts1(par + PAR_RED + 64 + (t3 >> 4) * 32 + ((lane & 1) * 4 + (lane & 2) + ((lane >> 2) & 1)) * 4, __float_as_uint(y0));
      bar_sync(4, 128);
      if (t3 < 4) {
        y0 = 0.f; y1 = 0.f;
#pragma unroll
        for (int w4 = 0; w4 < 7; w4++) {
          const uint2 v = lds2(par + PAR_RED + 64 + w4 * 32 + t3 * 8);
          y0 += __uint_as_float(v.x); y1 += __uint_as_float(v.y);
        }
        const uint2 gv = lds2(par + PAR_CONST + 16 + t3 * 8);
        const uint32_t upd = hmul2(pack_bf(y0, y1), pack_bf(rs, rs));
        *reinterpret_cast<uint32_t*>(P.out + (size_t)win.y * DM + b * 8 + t3 * 2) =
            hadd2(fx.x, hmul2(__byte_perm(gv.x, gv.y, 0x7632), hadd2(fh.x, upd)));
        if (b == 0 && t3 == 0) st_relaxed(&g_epoch, epoch + 1);
      }
      PROF(31, t3 == 0, 36);
    }
    cluster_wait();
  } else {
    const int wg = warp >> 2;

    uint32_t tag;
    {
      uint32_t* const pmod = g_modp + rank * 2 * DM + (b >> 1) * 32 + lane;
      uint32_t* const pln = g_ln1 + (rb * 128 + cj * 16 + warp) * 4;
      const uint32_t cv = ldg_nc1(P.c + rank * 512 + tid * 2);
      const uint32_t epoch = ld_relaxed(&g_epoch);
      if (warp == 0) st_relaxed(pmod, 0);
      if (lane == 0) { st_b128(pln, 0, 0, 0, 0); st_b128(pln + 32, 0, 0, 0, 0); }
      asm volatile("setmaxnreg.inc.sync.aligned.u32 232;");
      sts1(par + tid * 4, pack_bf(silu_f(bf_lo(cv)), silu_f(bf_hi(cv))));
      bar_sync(1, 320);
      tag = epoch % 3 + 1;
#pragma unroll
      for (int part = 0; part < 3; part++) {
        if (part != 1) {
          const uint32_t xa = base + (2 + part / 2) * GST_BYTES + warp * 2048 + lane * 16;
          mbar_wait(bar_hx + part * 4, 0);
          float s0 = 0.f, s1 = 0.f, q0 = 0.f, q1 = 0.f;
#pragma unroll
          for (int q = 0; q < 4; q++) {
            const uint4 xv = lds4(xa + q * 512);
            const uint32_t u[4] = {xv.x, xv.y, xv.z, xv.w};
#pragma unroll
            for (int e = 0; e < 4; e++) { const float lo = bf_lo(u[e]), hi = bf_hi(u[e]); s0 += lo; s1 += hi; q0 += lo * lo; q1 += hi * hi; }
          }
          s0 += s1; q0 += q1;
#pragma unroll
          for (int o = 16; o > 0; o >>= 1) { s0 += __shfl_xor_sync(0xffffffffu, s0, o); q0 += __shfl_xor_sync(0xffffffffu, q0, o); }
          const float mean = s0 * (1.f / DM);
          float mb, sd;
          ln_scalars(mean, fmaxf(q0 * (1.f / DM) - mean * mean, 0.f), mb, sd);
          uint32_t ih, il;
          split_inv(sd, ih, il);
          if (lane == 0) st_b128(pln + part * 16, pack_bf(mb, mb), ih, il, tag);
          PROF(1, tid == 0 && part == 2, 4);
        } else {
          float acc[8];
#pragma unroll
          for (int e = 0; e < 8; e++) acc[e] = 0.f;
          const uint32_t wa = stage + (tid >> 2) * 64 + (((tid ^ (tid >> 3)) & 3) << 4), sa = par + (tid >> 3) * 4, sh = (tid & 4) ? 0x3244 : 0x1044;
          mbar_wait(bar_hw, 0);
#pragma unroll
          for (int p = 0; p < 8; p++) {
            const uint4 w = lds4(wa + p * 4096);
            const float s = __uint_as_float(__byte_perm(lds1(sa + p * 128), 0, sh));
            acc[0] += s * bf_lo(w.x); acc[1] += s * bf_hi(w.x); acc[2] += s * bf_lo(w.y); acc[3] += s * bf_hi(w.y);
            acc[4] += s * bf_lo(w.z); acc[5] += s * bf_hi(w.z); acc[6] += s * bf_lo(w.w); acc[7] += s * bf_hi(w.w);
          }
#pragma unroll
          for (int e = 0; e < 4; e++) {
            const bool up = lane & 16;
            acc[e] = (up ? acc[e + 4] : acc[e]) + __shfl_xor_sync(0xffffffffu, up ? acc[e] : acc[e + 4], 16);
          }
#pragma unroll
          for (int e = 0; e < 2; e++) {
            const bool up = lane & 8;
            acc[e] = (up ? acc[e + 2] : acc[e]) + __shfl_xor_sync(0xffffffffu, up ? acc[e] : acc[e + 2], 8);
          }
          {
            const bool up = lane & 4;
            acc[0] = (up ? acc[1] : acc[0]) + __shfl_xor_sync(0xffffffffu, up ? acc[0] : acc[1], 4);
          }
          sts1(base + 2 * GST_BYTES + warp * 2048 + ((lane & 3) * 8 + (lane >> 2)) * 4, __float_as_uint(acc[0]));
          bar_sync(1, 256);
          if (warp == 0) {
            float s = 0.f;
#pragma unroll
            for (int w8 = 0; w8 < 8; w8++) s += __uint_as_float(lds1(base + 2 * GST_BYTES + w8 * 2048 + lane * 4));
            st_relaxed(pmod, (__float_as_uint(s) & ~3u) | tag);
          }
          PROF(1, tid == 0, 3);
        }
      }
      cluster_wait();
      if (wg == 1) bar_arrive(2, 256);
    }

    float f0 = 0.f, f1 = 0.f;
    const uint32_t rempty = lane < 2 ? mapa(bempty, lane & 1) : 0;
    constexpr uint32_t GE = NSLOT * 8 + 32;
    float o[64], s[64];
#pragma unroll 1
    for (int ps = 0; ps < 3; ps++) {
      {
        const uint32_t xt = ps == 1 ? XT1 : XT2, wt = ps == 1 ? WT1 : WT2;
        const int nst = ps == 2 ? 28 : 14;
        if (ps == 0) {
          float ga[64], gb[64];
#pragma unroll
          for (int i = 0; i < 64; i++) { ga[i] = 0.f; gb[i] = 0.f; }
          uint32_t a[2][16];
          const uint32_t l = fresh_lane();
          uint32_t fa[4];
#pragma unroll
          for (int kk = 0; kk < 4; kk++) fa[kk] = (base + wg * 8192 + frag_offset(warp)) ^ (kk * 32);
          const uint32_t mt = par + (l & 3) * 16;
          auto fetch = [&](int i, uint32_t (&f)[16], uint32_t z) {
            mbar_wait(xfull + (i & 3) * 8, i >> 2);
#pragma unroll
            for (int kk = 0; kk < 4; kk++) ldmatrix4(fa[kk] + (i & 3) * GST_BYTES + z, f[4 * kk], f[4 * kk + 1], f[4 * kk + 2], f[4 * kk + 3]);
          };
          uint4 r0, r1;
          {
            const uint32_t t7 = (warp & 3) * 32 + l;
            const uint32_t* pm = g_modp + wg * DM + ((cj * 128 + t7 * 4) & (DM - 1));
            const uint32_t* pr = g_ln1 + (rb * 128 + warp * 16 + (l >> 2)) * 4;
            uint4 m0 = ld_relaxed4(pm), m1 = ld_relaxed4(pm + 2 * DM);
            r0 = ld_b128(pr); r1 = ld_b128(pr + 32);
            fetch(0, a[0], 0); fetch(1, a[1], 0);
            uint32_t n = 0;
            bool written = false;
#pragma unroll 1
            while (true) {
              uint32_t miss;
              asm volatile("{ .reg .pred p0, p1, p2, p3; .reg .b32 t, u;\n"
                           "lop3.b32 t, %1, %2, %19, 0x7e; lop3.b32 u, %3, %4, %19, 0x7e; or.b32 t, t, u; and.b32 t, t, 3; setp.ne.u32 p0, t, 0;\n"
                           "lop3.b32 t, %5, %6, %19, 0x7e; lop3.b32 u, %7, %8, %19, 0x7e; or.b32 t, t, u; and.b32 t, t, 3; setp.ne.u32 p1, t, 0;\n"
                           "setp.ne.u32 p2, %12, %19; setp.ne.u32 p3, %16, %19;\n"
                           "@p0 ld.relaxed.gpu.global.v4.u32 {%1, %2, %3, %4}, [%17];\n"
                           "@p1 ld.relaxed.gpu.global.v4.u32 {%5, %6, %7, %8}, [%17 + 8192];\n"
                           "@p2 ld.relaxed.gpu.global.v4.u32 {%9, %10, %11, %12}, [%18];\n"
                           "@p3 ld.relaxed.gpu.global.v4.u32 {%13, %14, %15, %16}, [%18 + 128];\n"
                           "or.pred p0, p0, p1; or.pred p2, p2, p3; vote.sync.any.pred p0, p0, 0xffffffff; vote.sync.any.pred p2, p2, 0xffffffff;\n"
                           "selp.u32 t, 1, 0, p0; selp.u32 u, 2, 0, p2; or.b32 %0, t, u; }"
                           : "=r"(miss), "+r"(m0.x), "+r"(m0.y), "+r"(m0.z), "+r"(m0.w), "+r"(m1.x), "+r"(m1.y), "+r"(m1.z), "+r"(m1.w),
                             "+r"(r0.x), "+r"(r0.y), "+r"(r0.z), "+r"(r0.w), "+r"(r1.x), "+r"(r1.y), "+r"(r1.z), "+r"(r1.w)
                           : "l"(pm), "l"(pr), "r"(tag) : "memory");
              if (!(miss & 1) && !written) {
                written = true;
                float c0 = untag_sum(m0.x, m1.x), c1 = untag_sum(m0.y, m1.y), c2 = untag_sum(m0.z, m1.z), c3 = untag_sum(m0.w, m1.w);
                if (wg) { c0 = 1.f + rbf(c0); c1 = 1.f + rbf(c1); c2 = 1.f + rbf(c2); c3 = 1.f + rbf(c3); }
                const uint32_t d = par + (t7 >> 2) * 64 + (t7 & 1) * 32 + (t7 & 2) * 2 + (wg ? 0 : 8);
                sts1(d, pack_bf(c0, c1));
                sts1(d + 16, pack_bf(c2, c3));
                mbar_arrive(bar_mod);
              }
              if (!miss) break;
              watchdog(n);
            }
          }
          const uint32_t zero = r0.w ^ tag;
          auto normalize = [&](uint32_t (&f)[16]) {
#pragma unroll
            for (int k = 0; k < 16; k += 2) { f[k] = ln_norm(f[k], r0.x, r0.y, r0.z); f[k + 1] = ln_norm(f[k + 1], r1.x, r1.y, r1.z); }
          };
          auto modulate = [&](int i, uint32_t (&f)[16]) {
#pragma unroll
            for (int kk = 0; kk < 4; kk++) {
              const uint4 m = lds4(mt + i * 256 + kk * 64);
              f[4 * kk] = MODUL(f[4 * kk], m.x, m.z); f[4 * kk + 1] = MODUL(f[4 * kk + 1], m.x, m.z);
              f[4 * kk + 2] = MODUL(f[4 * kk + 2], m.y, m.w); f[4 * kk + 3] = MODUL(f[4 * kk + 3], m.y, m.w);
            }
            keep(f);
            mbar_arrive_pred(xempty + (i & 3) * 8, l == 0);
          };
          auto publish = [&](int u, uint32_t (&f)[16]) {
#pragma unroll
            for (int kk = 0; kk < 4; kk++) stmatrix4(fa[kk] + OFF_STAGE + u * UNIT, f[4 * kk], f[4 * kk + 1], f[4 * kk + 2], f[4 * kk + 3]);
            __syncwarp();
            mbar_arrive_pred(bar_hpub + u * 8, l == 0);
          };
          auto multiply = [&](int i, uint32_t (&f)[16]) {
            mbar_wait(gfull + (i & 3) * 8, i >> 2);
            const uint64_t db = make_desc(base + (i & 3) * GST_BYTES + UNIT, 8192, 1024);
            wg_fence();
#pragma unroll
            for (int kk = 0; kk < 4; kk++) mma256_rs(ga, gb, f[4 * kk], f[4 * kk + 1], f[4 * kk + 2], f[4 * kk + 3], db + kk * 128);
            wg_commit();
          };
          auto next = [&](int i, uint32_t (&f)[16]) {
            wg_wait<1>();
            mbar_arrive_cl(rempty, GE + ((i + 2) & 3) * 8);
            uint32_t z = zero;
#pragma unroll
            for (int k = 0; k < 16; k += 2) asm volatile("lop3.b32 %0, %1, %2, %0, 0xA8;" : "+r"(z) : "r"(f[k]), "r"(f[k + 1]));
            fetch(i, f, z);
            normalize(f); modulate(i, f); multiply(i, f);
          };
          normalize(a[0]); normalize(a[1]);
          keep(a[0]); keep(a[1]);
          mbar_wait(bar_mod, 0);
          PROF(1, tid == 0, 2);
          modulate(0, a[0]); multiply(0, a[0]); publish(0, a[0]);
          modulate(1, a[1]); multiply(1, a[1]); publish(1, a[1]);
#pragma unroll 1
          for (int i = 2; i < NRS; i += 2) { next(i, a[0]); next(i + 1, a[1]); }
          wg_wait<1>();
          mbar_arrive_cl(rempty, GE + ((NRS + 2) & 3) * 8);
#pragma unroll 1
          for (int i = NRS; i < 14; i++) {
            mbar_wait(xfull + (i & 3) * 8, (i >> 2) & 1);
            mbar_wait(gfull + (i & 3) * 8, (i >> 2) & 1);
            const uint32_t xa = base + (i & 3) * GST_BYTES;
            const uint64_t da = make_desc(xa + wg * 8192, 16, 1024), db = make_desc(xa + UNIT, 8192, 1024);
            if (i == 13) bar_sync(2 + wg, 256);
            wg_fence();
#pragma unroll
            for (int kk = 0; kk < 4; kk++) mma256_ss(ga, gb, da + kk * 2, db + kk * 128, 1);
            wg_commit();
            if (i == 13) bar_arrive(3 - wg, 256);
            wg_wait<1>();
            uint32_t z = zero;
#pragma unroll
            for (int k = 0; k < 16; k += 2) asm volatile("lop3.b32 %0, %1, %2, %0, 0xA8;" : "+r"(z) : "r"(a[1][k]), "r"(a[1][k + 1]));
            mbar_arrive_cl(rempty, GE + ((i + 3) & 3) * 8 + z);
            mbar_arrive_pred(xempty + ((i + 3) & 3) * 8, l == 0 && i != NRS);
          }
          mbar_wait(xfull + 16, 1);
          wg_wait<0>();
          keep(ga); keep(gb);
#pragma unroll
          for (int i = 0; i < 64; i++) {
            asm volatile("mov.b32 %0, %1;" : "=f"(s[i]) : "f"(ga[i]));
            asm volatile("mov.b32 %0, %1;" : "=f"(o[i]) : "f"(gb[i]));
          }
        } else {
          float ga[64], gb[64];
#pragma unroll
          for (int i = 0; i < 64; i++) {
            asm volatile("mov.b32 %0, %1;" : "=f"(ga[i]) : "f"(s[i]));
            asm volatile("mov.b32 %0, %1;" : "=f"(gb[i]) : "f"(o[i]));
          }
#pragma unroll 1
          for (int i = 0; i < nst; i++) {
            mbar_wait(gfull + (i & 3) * 8, (i >> 2) & 1);
            const uint64_t da = make_desc(base + unit_of(xt, i & 3) + wg * 8192, 16, 1024), db = make_desc(base + unit_of(wt, i & 3), 8192, 1024);
            if (i == nst - 1) bar_sync(2 + wg, 256);
            wg_fence();
#pragma unroll
            for (int kk = 0; kk < 4; kk++) mma256_ss(ga, gb, da + kk * 2, db + kk * 128, kk ? 1 : i);
            wg_commit();
            if (i == nst - 1) bar_arrive(3 - wg, 256);
            wg_wait<1>();
            mbar_arrive_cl(rempty, GE + ((i + 3) & 3) * 8, i != 0);
            PROF(4, tid == 0 && (i & 3) == 0, 40 + (ps - 1) * 4 + i / 4);
          }
          wg_wait<0>();
          keep(ga); keep(gb);
#pragma unroll
          for (int i = 0; i < 64; i++) {
            asm volatile("mov.b32 %0, %1;" : "=f"(s[i]) : "f"(ga[i]));
            asm volatile("mov.b32 %0, %1;" : "=f"(o[i]) : "f"(gb[i]));
          }
        }
        mbar_arrive_cl(rempty, GE + (ps == 2 ? 24 : 8));
        if (ps == 2) break;
      }
      const uint32_t qw = base + wg * 8192, qt = QT >> (16 * ps), at = ps ? AT1 : AT0;
      {
        const uint32_t wt = ps ? WT1 : WT0;
        const uint64_t da0 = make_desc(qw + unit_of(qt, 2), 16, 1024), da1 = make_desc(qw + unit_of(qt, 3), 16, 1024);
        const uint64_t db0 = make_desc(base + unit_of(wt, 2), 8192, 1024), db1 = make_desc(base + unit_of(wt, 3), 8192, 1024);
        mbar_wait(gfull + 16, 1);
        bar_sync(2 + wg, 256);
        wg_fence();
#pragma unroll
        for (int kk = 0; kk < 4; kk++) mma_ss<1>(s, da0 + kk * 2, db0 + kk * 128, 1);
        wg_commit();
        mbar_wait(xfull + 24, 1);
        mbar_wait(gfull + 24, 1);
        wg_fence();
#pragma unroll
        for (int kk = 0; kk < 4; kk++) mma_ss<1>(s, da1 + kk * 2, db1 + kk * 128, 1);
        wg_commit();
        bar_arrive(3 - wg, 256);
        mbar_wait(ps == 0 ? bar_pread : bar_ofree + 8, 0);
        mbar_wait(bfull, 0);
        wg_wait<0>();
        keep(s);
        PROF(2, tid == 0, 8 + ps * 8);
        store_chunk<0>(s, qw + unit_of(qt, 0) + frag_offset(warp));
        store_chunk<1>(s, qw + unit_of(qt, 1) + frag_offset(warp));
        fence_async_smem();
        bar_sync(2 + wg, 256);
        wg_fence();
        issue_qk(s, qw + unit_of(qt, 0), qw + unit_of(qt, 1), base + unit_of(at, 0));
        wg_commit();
#pragma unroll
        for (int kk = 0; kk < 8; kk++) mma_ss<1>(o, (kk < 4 ? da0 : da1) + (kk & 3) * 2, (kk < 4 ? db0 : db1) + UNIT / 16 + (kk & 3) * 128, 1);
        wg_commit();
        bar_arrive(3 - wg, 256);
        wg_wait<1>();
        keep(s);
        mbar_arrive_cl(rempty, 0);
      }
      PROF(4, tid == 0 && ps == 1, 61);
      float l0 = 0.25f, l1 = 0.25f;
      auto step = [&](auto odd_c, const int j, uint32_t (&pw)[32], uint32_t (&pr)[32]) {
        constexpr bool ODD = decltype(odd_c)::value;
        const bool first = !ODD && (j & 2) == 0, last = ODD && j == 7;
        const uint32_t ph = (j >> 1) & 1;
        float i0, i1, a0, a1;
        if (first) { i0 = inv_quad_sum(l0); i1 = inv_quad_sum(l1); l0 = 0.f; l1 = 0.f; }
        bool redo = !ODD && (j | ps) == 0, again = false;
        while (true) {
          if (redo) {
            float m0 = fmaxf(s[0], s[1]), m1 = fmaxf(s[2], s[3]);
#pragma unroll
            for (int i = 1; i < 16; i++) { m0 = fmaxf(m0, fmaxf(s[4 * i], s[4 * i + 1])); m1 = fmaxf(m1, fmaxf(s[4 * i + 2], s[4 * i + 3])); }
            m0 = fmaxf(m0, __shfl_xor_sync(0xffffffffu, m0, 1)); m1 = fmaxf(m1, __shfl_xor_sync(0xffffffffu, m1, 1));
            m0 = fmaxf(m0, __shfl_xor_sync(0xffffffffu, m0, 2)); m1 = fmaxf(m1, __shfl_xor_sync(0xffffffffu, m1, 2));
            m0 *= SCL2; m1 *= SCL2;
            if (!first) {
              m0 = fmaxf(m0, f0); m1 = fmaxf(m1, f1);
              const float c0 = ex2(f0 - m0), c1 = ex2(f1 - m1);
              l0 *= c0; l1 *= c1;
              wg_wait<0>();
              keep(o);
#pragma unroll
              for (int i = 0; i < 16; i++) { o[4 * i] *= c0; o[4 * i + 1] *= c0; o[4 * i + 2] *= c1; o[4 * i + 3] *= c1; }
            }
            f0 = m0; f1 = m1;
          }
          float b0 = 0.f, b1 = 0.f;
          a0 = 0.f; a1 = 0.f;
#pragma unroll
          for (int i = 0; i < 16; i++) {
            const float e0 = ex2(fmaf(s[4 * i], SCL2, -f0)), e1 = ex2(fmaf(s[4 * i + 1], SCL2, -f0));
            const float e2 = ex2(fmaf(s[4 * i + 2], SCL2, -f1)), e3 = ex2(fmaf(s[4 * i + 3], SCL2, -f1));
            a0 += e0; b0 += e1; a1 += e2; b1 += e3;
            pw[2 * i] = pack_bf(e0, e1); pw[2 * i + 1] = pack_bf(e2, e3);
            if (i == VREL) {
#pragma unroll
              for (int k = 0; k < 2 * VREL + 2; k++) asm volatile("" : "+r"(pw[k])::"memory");
              mbar_wait(bar_mod, 0);
              wg_wait<0>();
              mbar_arrive_cl(rempty, ODD ? 16 : (j ? 0 : GE + 16), !again);
              if (!ODD) mbar_arrive_cl(rempty, GE + 24, !again && j == 0);
#pragma unroll
              for (int k = 4 * VREL + 4; k < 64; k++) asm volatile("" : "+f"(s[k])::"memory");
            }
          }
          a0 += b0; a1 += b1;
          if (redo) break;
          redo = __any_sync(0xffffffffu, !(a0 + a1 < 0x1p70f));
          if (first) {
            uint32_t m0 = __ballot_sync(0xffffffffu, a0 > 0x1p-50f), m1 = __ballot_sync(0xffffffffu, a1 > 0x1p-50f);
            m0 |= m0 >> 1; m1 |= m1 >> 1; m0 |= m0 >> 2; m1 |= m1 >> 2;
            redo = redo || (m0 & m1 & 0x11111111u) != 0x11111111u;
          }
          if (!redo) break;
          again = true;
        }
        l0 += a0; l1 += a1;
        keep(pw);
        keep(o);
        const uint32_t qo = qt >> (j ? 0 : 8);
        if (first) store_chunk<0>(o, i0, i1, qw + unit_of(qo, 0) + frag_offset(warp));
        keep(o);
        mbar_wait(bfull + (ODD ? 24 : 8), ph);
        bar_sync(2 + wg, 256);
        if (!last) {
          const uint32_t qn = qt >> (j >= 3 ? 8 : 0);
          wg_fence();
          issue_qk(s, qw + unit_of(qn, 0), qw + unit_of(qn, 1), base + unit_of(at, ODD ? 3 : 1));
          wg_commit();
          mbar_wait(bfull + (ODD ? 0 : 16), ODD ? ph ^ 1 : ph);
        }
        if (first) { store_chunk<1>(o, i0, i1, qw + unit_of(qo, 1) + frag_offset(warp)); keep(o); }
        wg_fence();
        issue_pv(o, pw, base + unit_of(at, ODD ? (last ? 3 : 0) : 2), !first);
        wg_commit();
        bar_arrive(3 - wg, 256);
        wg_wait<1>();
        keep(s);
        mbar_arrive_cl(rempty, ODD ? 24 : 8, !last);
        if (first) { fence_async_smem(); mbar_arrive_pred(bar_ofull + wg * 8, j); }
        PROF(4, tid == 0 && ps == 1, 51 + j);
      };
      uint32_t pa[32], pb[32];
#pragma unroll 1
      for (int j = 0; j < 8; j += 2) {
        step(std::false_type{}, j, pa, pb);
        step(std::true_type{}, j + 1, pb, pa);
      }
      {
        const float i0 = inv_quad_sum(l0), i1 = inv_quad_sum(l1);
        wg_wait<0>();
        keep(o);
        mbar_arrive_cl(rempty, 24);
        store_chunk<0>(o, i0, i1, qw + unit_of(qt, 2) + frag_offset(warp));
        store_chunk<1>(o, i0, i1, qw + unit_of(qt, 3) + frag_offset(warp));
        fence_async_smem();
        mbar_arrive(bar_ofull + 16 + wg * 8);
      }
      PROF(2, tid == 0, 10 + ps * 8);
    }

    const int ln = fresh_lane(), g = ln >> 2, tq = ln & 3, ct = warp * 32 + ln;
    const bool lane0 = ln == 0;
    const int lrow0 = warp * 16 + g;
    const int grow0 = rb * 128 + lrow0;
    const uint32_t res = base + OFF_RES, trow = res + wg * 8192 + frag_offset(warp);
    uint32_t xr[32];
    uint4 sv[4], own;
    uint32_t* sp[4];
#pragma unroll
    for (int k = 0; k < 4; k++) sp[k] = g_stats + ((((tq >> 1) * 4 + k) ^ cj) * SEQ + grow0 + (tq & 1) * 8) * 4;
    {
      const uint64_t da = make_desc(base + wg * 8192, 16, 1024), db = make_desc(base, 8192, 1024);
      constexpr int U = UNIT / 16;
#define HALF_STAGE(acc, xu, wu) _Pragma("unroll") for (int kk = 0; kk < 4; kk++) mma_ss<1>(acc, da + (xu) * U + kk * 2, db + (wu) * U + kk * 128, 1)
      PROF(10, ct == PT, 19); STAMP(0);
      cluster_arrive();
      mbar_wait(gfull, 1);
      mbar_wait(gfull + 8, 1);
      bar_sync(2 + wg, 256);
      wg_fence();
      HALF_STAGE(o, 7, 1);
      HALF_STAGE(o, 8, 3);
      wg_commit();
      STAMP(16);
      mbar_wait(gfull + 16, 1);
      STAMP(17);
      wg_fence();
      HALF_STAGE(o, 6, 11);
      wg_commit();
      bar_arrive(3 - wg, 256);
      mbar_wait(bar_par, 0);
      uint32_t* xo = g_xch + ((size_t)b * 8 * 256 + ct) * 4;
      const uint32_t* xi = g_xch + ((size_t)(b ^ 2) * 8 * 256 + ct) * 4;
      const uint32_t par1 = (~lds1(par + PAR_CONST + 4) & 1) << 16;
      uint32_t ga[16];
      uint4 bw[8];
#define LOAD_PAR _Pragma("unroll") for (int i = 0; i < 8; i++) {                                                               \
        ga[2 * i] = lds1(par + PAR_T2 + i * 128 + tq * 16 + 12); ga[2 * i + 1] = lds1(par + PAR_T2 + i * 128 + 64 + tq * 16 + 12); \
        bw[i] = lds4(par + PAR_T1 + i * 64 + tq * 16);                                                                          \
        if (!(g & 1)) { bw[i].x = 0x3f803f80u; bw[i].y = 0x3f803f80u; }                                                         \
      }
      if (PPOS == 0) LOAD_PAR
      wg_wait<1>();
      mbar_arrive_pred(bar_rel, lane0);
      wg_wait<0>();
      keep(o);
      mbar_arrive_pred(bar_ring, lane0);
      PROF(8, ct == PT, 20); STAMP(1);
#define SEND(i) st_b128(xo + (i) * 1024, (pack_bf(o[8 * (i)], o[8 * (i) + 1]) & ~0x10000u) | par1, pack_bf(o[8 * (i) + 2], o[8 * (i) + 3]), \
                        pack_bf(o[8 * (i) + 4], o[8 * (i) + 5]), pack_bf(o[8 * (i) + 6], o[8 * (i) + 7]))
#pragma unroll
      for (int i = 0; i < NS1; i++) SEND(i);
      PROF(8, ct == PT, 21); STAMP(2);
      bar_sync(2 + wg, 256);
      wg_fence();
      HALF_STAGE(s, 7, 0);
      HALF_STAGE(s, 8, 2);
      HALF_STAGE(s, 6, 10);
      wg_commit();
      bar_arrive(3 - wg, 256);
      STAMP(18);
      mbar_wait(gfull + 24, 1);
#pragma unroll
      for (int i = NS1; i < 8; i++) SEND(i);
      uint4 v[8];
#pragma unroll
      for (int i = 0; i < 4; i++) v[i] = ld_b128(xi + i * 1024);
      if (PPOS == 1) LOAD_PAR
      STAMP(19);
      mbar_wait(bar_xres, 0);
      wg_wait<0>();
      mbar_arrive_pred(bar_ring + 8, lane0);
      bar_sync(2 + wg, 256);
      STAMP(20);
#pragma unroll
      for (int i = 4; i < 8; i++) v[i] = ld_b128(xi + i * 1024);
      mbar_wait(bar_xres, 0);
      wg_fence();
      HALF_STAGE(s, 9, 4);
      wg_commit();
      mbar_wait(bar_rx, 0);
      wg_fence();
      HALF_STAGE(s, 1, 5);
      wg_commit();
      bar_arrive(3 - wg, 256);
      STAMP(21);
      wg_wait<0>();
      keep(s);
      mbar_arrive_pred(bar_ring + 16, lane0);
      PROF(10, ct == PT, 23); STAMP(4);
#pragma unroll
      for (int i = 0; i < 16; i += 2) ldmatrix4((trow ^ ((i & 7) << 4)) + (i >> 3) * 16384, xr[2 * i], xr[2 * i + 1], xr[2 * i + 2], xr[2 * i + 3]);
      if (PPOS == 2) LOAD_PAR
      uint32_t pk[32];
      pack_p(s, pk);
      keep(pk);
      {
        uint32_t n = 0, miss;
        do {
          miss = 0;
#pragma unroll
          for (int i = 0; i < 8; i++) miss |= v[i].x ^ par1;
          miss = __any_sync(0xffffffffu, miss & 0x10000u);
          if (miss) {
#pragma unroll
            for (int i = 0; i < 8; i++)
              asm volatile("{ .reg .pred p; .reg .b32 t; xor.b32 t, %0, %5; and.b32 t, t, 0x10000; setp.ne.u32 p, t, 0;\n"
                           "@p ld.relaxed.gpu.global.v4.u32 {%0, %1, %2, %3}, [%4]; }"
                           : "+r"(v[i].x), "+r"(v[i].y), "+r"(v[i].z), "+r"(v[i].w) : "l"(xi + i * 1024), "r"(par1) : "memory");
          }
          watchdog(n);
        } while (miss);
      }
      PROF(8, ct == PT, 22); STAMP(3);
#pragma unroll
      for (int k = 0; k < 4; k++) sv[k] = ESV ? ld_b128(sp[k]) : make_uint4(0, 0, 0, 0);
      float ds[4] = {0.f, 0.f, 0.f, 0.f}, dl[4] = {0.f, 0.f, 0.f, 0.f}, q0[4] = {0.f, 0.f, 0.f, 0.f}, q1[4] = {0.f, 0.f, 0.f, 0.f};
#pragma unroll
      for (int i = 0; i < 8; i++) {
        const uint32_t u0 = hfma2(ga[2 * i], hadd2(pk[4 * i], v[i].x & ~0x10000u), xr[4 * i]);
        const uint32_t u1 = hfma2(ga[2 * i], hadd2(pk[4 * i + 1], v[i].y), xr[4 * i + 1]);
        const uint32_t u2 = hfma2(ga[2 * i + 1], hadd2(pk[4 * i + 2], v[i].z), xr[4 * i + 2]);
        const uint32_t u3 = hfma2(ga[2 * i + 1], hadd2(pk[4 * i + 3], v[i].w), xr[4 * i + 3]);
        xr[4 * i] = u0; xr[4 * i + 1] = u1; xr[4 * i + 2] = u2; xr[4 * i + 3] = u3;
        mma16816(ds, u0, u1, u2, u3, bw[i].x, bw[i].y);
        mma16816(dl, u0, u1, u2, u3, bw[i].z, bw[i].w);
        mma16816(q0, u0, u1, u2, u3, u0, u2);
        mma16816(q1, u0, u1, u2, u3, u1, u3);
      }
      const float sqa = __shfl_sync(0xffffffffu, (g & 1) ? q0[1] : q0[0], g * 4 + (g >> 1));
      const float sqb = __shfl_sync(0xffffffffu, (g & 1) ? q1[3] : q1[2], g * 4 + (g >> 1));
      own = (tq & 1) ? make_uint4(__float_as_uint(ds[2]), __float_as_uint(sqb), __float_as_uint(ds[3] + dl[3]), tag)
                                 : make_uint4(__float_as_uint(ds[0]), __float_as_uint(sqa), __float_as_uint(ds[1] + dl[1]), tag);
      if (tq < 2) st_b128(sp[0], own.x, own.y, own.z, own.w);
    }
    PROF(8, ct == PT, 29); STAMP(5);
    uint32_t mm, ih, il;
    float rbest;
    uint32_t wf[128];
    const uint32_t frow = (ln & 7) + (ln >> 4) * 8;
    const uint32_t wfo = base + (warp & 1) * 8192 + frow * 64 + ((((ln >> 3) & 1) ^ ((frow >> 1) & 3)) << 4);
#define LOAD_WF(m) _Pragma("unroll") for (int f = 0; f < 16; f++) {                                                   \
      const int r = ((f >> 1) * 4 + (m) * 2 + (f & 1)) * 4;                                                           \
      ldmatrix4t(((wfo + unit_of((m) ? FT_U : FT_G, warp >> 1)) ^ ((f & 1) * 32)) + (f >> 1) * 1024, wf[r], wf[r + 1], wf[r + 2], wf[r + 3]); \
    }
    bool early, wait1;
    {
#pragma unroll
      for (int i = 0; i < 16; i += 2) stmatrix4((trow ^ ((i & 7) << 4)) + (i >> 3) * 16384, xr[2 * i], xr[2 * i + 1], xr[2 * i + 2], xr[2 * i + 3]);
      const uint4 cst = lds4(par + PAR_CONST);
      const float A1 = __uint_as_float(cst.x), A2 = __uint_as_float(cst.z);
      uint32_t n = 0;
      early = false; wait1 = false;
#pragma unroll 1
      while (true) {
        uint32_t miss;
        asm volatile("{ .reg .pred p0, p1, p2, p3; .reg .b64 u, v; .reg .b128 w;\n"
                     "setp.ge.u32 p0, %22, 2; setp.ne.and.u32 p0, %4, %21, p0; setp.ne.u32 p1, %8, %21; setp.ne.u32 p2, %12, %21; setp.ne.u32 p3, %16, %21;\n"
                     "@p0 ld.relaxed.gpu.global.v4.u32 {%1, %2, %3, %4}, [%17];\n"
                     "@p1 ld.relaxed.gpu.global.v4.u32 {%5, %6, %7, %8}, [%18];\n"
                     "@p2 ld.relaxed.gpu.global.v4.u32 {%9, %10, %11, %12}, [%19];\n"
                     "@p3 ld.relaxed.gpu.global.v4.u32 {%13, %14, %15, %16}, [%20];\n"
                     "or.pred p0, p0, p1; or.pred p2, p2, p3; or.pred p0, p0, p2; vote.sync.any.pred p0, p0, 0xffffffff; selp.u32 %0, 1, 0, p0; }"
                     : "=r"(miss), "+r"(sv[0].x), "+r"(sv[0].y), "+r"(sv[0].z), "+r"(sv[0].w), "+r"(sv[1].x), "+r"(sv[1].y), "+r"(sv[1].z), "+r"(sv[1].w),
                       "+r"(sv[2].x), "+r"(sv[2].y), "+r"(sv[2].z), "+r"(sv[2].w), "+r"(sv[3].x), "+r"(sv[3].y), "+r"(sv[3].z), "+r"(sv[3].w)
                     : "l"(sp[0]), "l"(sp[1]), "l"(sp[2]), "l"(sp[3]), "r"(tag), "r"(tq) : "memory");
        if (!miss) break;
        wait1 = true;
        if (!early && (b >= NFFN || __all_sync(0xffffffffu, mbar_test(bar_box + (warp >> 1) * 8, 0)))) {
          early = true;
          LOAD_WF(0);
          __syncwarp();
          mbar_arrive_pred(bar_gate, lane0);
        }
        watchdog(n);
      }
      const uint4 v0 = tq < 2 ? own : sv[0], v1 = sv[1], v2 = sv[2], v3 = sv[3];
      PROF(8, ct == PT, 30); STAMP(6);
      float su = (__uint_as_float(v0.x) + __uint_as_float(v1.x)) + (__uint_as_float(v2.x) + __uint_as_float(v3.x));
      float sq = (__uint_as_float(v0.y) + __uint_as_float(v1.y)) + (__uint_as_float(v2.y) + __uint_as_float(v3.y));
      float dt = (__uint_as_float(v0.z) + __uint_as_float(v1.z)) + (__uint_as_float(v2.z) + __uint_as_float(v3.z));
      su += __shfl_xor_sync(0xffffffffu, su, 2); sq += __shfl_xor_sync(0xffffffffu, sq, 2); dt += __shfl_xor_sync(0xffffffffu, dt, 2);
      const float m = su * (1.f / DM);
      float mb, sd;
      ln_scalars(m, fmaxf(sq * (1.f / DM) - m * m, 0.f), mb, sd);
      const float inv = rcp(sd);
      rbest = (dt - mb * A1) * inv + A2;
      mm = pack_bf(mb, mb);
      ih = pack_bf(inv, inv);
      const float lo = inv - bf_lo(ih);
      il = pack_bf(lo, lo);
    }
    int ibest;
    {
      const uint32_t bits = __float_as_uint(rbest);
      const uint32_t key = (((int)bits < 0 ? ~bits : bits | 0x80000000u) & ~0x1ffu) | ((127 - lrow0 - (tq & 1) * 8) << 2) | tag;
      sts1(par + PAR_RED + warp * 4, __reduce_max_sync(0xffffffffu, key));
      PROF(8, ct == PT, 38); STAMP(7);
      uint32_t waited;
      asm volatile("{ .reg .pred p, q; setp.ne.u32 p, %1, 0; barrier.cta.red.or.pred q, 1, 256, p; selp.u32 %0, 1, 0, q; }" : "=r"(waited) : "r"((uint32_t)(wait1 && (wg || CW0))) : "memory");
      const uint4 ka = lds4(par + PAR_RED), kb = lds4(par + PAR_RED + 16);
      const uint32_t k2 = max(max(max(ka.x, ka.y), max(ka.z, ka.w)), max(max(kb.x, kb.y), max(kb.z, kb.w)));
      if (ct == 0 && ((cj & CWM) == 0 || (CWL && !waited))) st_relaxed(g_cand + rb, k2);
      ibest = 127 - ((k2 >> 2) & 127);
    }
    PROF(8, ct == PT, 39); STAMP(8);
    if ((ibest >> 4) == warp) {
      const int src = (ibest & 7) * 4 + ((ibest >> 3) & 1), ch = g * 2;
      const uint32_t cm = __shfl_sync(0xffffffffu, mm, src), ch_ = __shfl_sync(0xffffffffu, ih, src), cl = __shfl_sync(0xffffffffu, il, src);
      const uint32_t xa = res + (ch >> 3) * 16384 + ibest * 128 + (((ch & 7) ^ (ibest & 7)) << 4) + tq * 4;
      const uint32_t x0 = lds1(xa), x1 = lds1(xa ^ 16);
      const uint2 p0 = lds2(par + PAR_T2 + ch * 64 + tq * 16), p1 = lds2(par + PAR_T2 + ch * 64 + 64 + tq * 16);
      uint32_t* dst = g_row + rb * 2 * DM + cj * 128 + ln * 4;
      st_pairs(dst, ln_mod(x0, cm, ch_, cl, p0.x, p0.y), ln_mod(x1, cm, ch_, cl, p1.x, p1.y), tag);
      st_pairs(dst + DM, x0, x1, tag);
      __syncwarp();
    }
    PROF(8, ct == PT, 37); STAMP(9);
    const bool cand = (ibest >> 4) == warp;
    auto out_half = [&](int hf) {
      const uint32_t mm0 = __shfl_sync(0xffffffffu, mm, ln & ~1), mm1 = __shfl_sync(0xffffffffu, mm, ln | 1);
      const uint32_t ih0 = __shfl_sync(0xffffffffu, ih, ln & ~1), ih1 = __shfl_sync(0xffffffffu, ih, ln | 1);
      const uint32_t il0 = __shfl_sync(0xffffffffu, il, ln & ~1), il1 = __shfl_sync(0xffffffffu, il, ln | 1);
      uint32_t x[16];
#pragma unroll
      for (int i = 0; i < 8; i += 2) ldmatrix4((trow ^ (i << 4)) + hf * 16384, x[2 * i], x[2 * i + 1], x[2 * i + 2], x[2 * i + 3]);
#pragma unroll
      for (int i = 0; i < 8; i++) {
        const uint4 pv = lds4(par + PAR_T2 + (hf * 8 + i) * 64 + tq * 16);
        x[2 * i] = OMUL(OMUL(ln_norm(x[2 * i], mm0, ih0, il0), pv.x, pv.y), pv.z, x[2 * i]);
        x[2 * i + 1] = OMUL(OMUL(ln_norm(x[2 * i + 1], mm1, ih1, il1), pv.x, pv.y), pv.z, x[2 * i + 1]);
      }
#pragma unroll
      for (int i = 0; i < 8; i += 2) stmatrix4((trow ^ (i << 4)) + hf * 16384, x[2 * i], x[2 * i + 1], x[2 * i + 2], x[2 * i + 3]);
      if (!cand) fence_async_smem();
      __syncwarp();
      if (!cand && elect_one()) {
        tma2d_store(&maps.out, res + hf * 16384 + warp * 2048, cj * 128 + hf * 64, rb * 128 + warp * 16);
        asm volatile("cp.async.bulk.commit_group;" ::: "memory");
      }
    };
    if (LNP == 1 || (LNP == 2 && b >= NFFN)) out_half(0);
    uint32_t wd[64];
    const uint32_t wda = base + unit_of(FT_D, warp >> 1) + (warp & 1) * 8192 + frow * 128 + ((((ln >> 3) & 1) ^ (ln & 7)) << 4);
#define LOAD_WD(f) ldmatrix4t((wda ^ ((((f) >> 1) & 3) * 32)) + ((f) >> 3) * 4096 + ((f) & 1) * 2048, wd[4 * (f)], wd[4 * (f) + 1], wd[4 * (f) + 2], wd[4 * (f) + 3])
    if (!early) {
      if (b < NFFN) mbar_wait(bar_box + (warp >> 1) * 8, 0);
      LOAD_WF(0);
      __syncwarp();
      mbar_arrive_pred(bar_gate, lane0);
    }
    if (b < NFFN) {
      const uint32_t own = base + unit_of(FT_G, warp >> 1) + (warp & 1) * 8192;
      mbar_wait(bar_box + (4 + (warp >> 1)) * 8, 0);
      LOAD_WF(1);
      uint32_t* const ydst = g_ypart + ((size_t)(warp * 16 + tq * 2) * NFFN + b) * 8 + g;
      if (LNP == 2) out_half(0);
      PROF(8, ct == PT, 31); STAMP(10);
      mbar_wait(bar_box + (8 + (warp >> 1)) * 8, 0);
#pragma unroll
      for (int f = 0; f < WDE; f++) LOAD_WD(f);
      STAMP(11);
      mbar_wait(bar_sel, 0);
      PROF(8, ct == PT, 33); STAMP(12);
      float d[8][4];
#pragma unroll
      for (int i = 0; i < 4; i++) { d[i][0] = 0.f; d[i][1] = 0.f; d[i][2] = 0.f; d[i][3] = 0.f; }
#pragma unroll
      for (int ks = 0; ks < 8; ks++) {
        const uint2 hb = lds2(own + 256 + ks * 32 + tq * 8);
#pragma unroll
        for (int mt = 0; mt < 4; mt++) {
          const int r = ks * 16 + mt * 4;
          mma16816(d[mt], wf[r], wf[r + 1], wf[r + 2], wf[r + 3], hb.x, hb.y);
        }
      }
      sts2(own + (tq * 8 + g) * 8, __float_as_uint((tq & 2) ? ((tq & 1) ? d[1][2] : d[1][0]) : ((tq & 1) ? d[0][2] : d[0][0])),
           __float_as_uint((tq & 2) ? ((tq & 1) ? d[3][2] : d[3][0]) : ((tq & 1) ? d[2][2] : d[2][0])));
      bar_sync(1, 256);
      uint32_t ab[4];
      {
        float G = 0.f, U = 0.f;
        uint2 pv[8];
#pragma unroll
        for (int w8 = 0; w8 < 8; w8++) pv[w8] = lds2(base + ln * 8 + ((FT_G >> (w8 >> 1) * 4) & 15) * UNIT + (w8 & 1) * 8192);
#pragma unroll
        for (int w8 = 0; w8 < 8; w8 += 2) {
          G += __uint_as_float(pv[w8].x) + __uint_as_float(pv[w8 + 1].x);
          U += __uint_as_float(pv[w8].y) + __uint_as_float(pv[w8 + 1].y);
        }
#pragma unroll
        for (int f = WDE; f < 16; f++) LOAD_WD(f);
        const float act = rbf(silu_f(rbf(G))) * rbf(U);
        const uint32_t pk = pack_bf(act, __shfl_down_sync(0xffffffffu, act, 1));
#pragma unroll
        for (int i = 0; i < 4; i++) ab[i] = __shfl_sync(0xffffffffu, pk, i * 8 + tq * 2);
      }
      PROF(8, ct == PT, 34); STAMP(13);
#pragma unroll
      for (int mt = 0; mt < 8; mt++) {
        d[mt][0] = 0.f; d[mt][1] = 0.f; d[mt][2] = 0.f; d[mt][3] = 0.f;
        mma16816(d[mt], wd[mt * 8], wd[mt * 8 + 1], wd[mt * 8 + 2], wd[mt * 8 + 3], ab[0], ab[1]);
        mma16816(d[mt], wd[mt * 8 + 4], wd[mt * 8 + 5], wd[mt * 8 + 6], wd[mt * 8 + 7], ab[2], ab[3]);
      }
#pragma unroll
      for (int i = 0; i < 4; i++) {
        const int m4 = (i >> 1) * 4, e = (i & 1) * 2;
        const float y = (tq & 2) ? ((tq & 1) ? d[m4 + 3][e] : d[m4 + 2][e]) : ((tq & 1) ? d[m4 + 1][e] : d[m4][e]);
        st_relaxed(ydst + (m4 * 2 + (i & 1)) * NFFN * 8, tagf(y, tag));
      }
      PROF(8, ct == PT, 35); STAMP(14);
    }
    mbar_wait(bar_sel, 0);
    mbar_arrive_pred(bar_win, ct == 0);
    const int iwin = lds1(par + PAR_CONST + 60) & 0x7ff;
    if (LNP == 0) out_half(0);
    out_half(1);
    if (cand) {
      const int wrow0 = warp * 16;
#pragma unroll 2
      for (int p = 0; p < 8; p++) {
        const int row = 2 * p + (ln >> 4), ch = ln & 15;
        const uint4 v = lds4(res + (ch >> 3) * 16384 + (wrow0 + row) * 128 + (((ch & 7) ^ (row & 7)) << 4));
        if (rb * 128 + wrow0 + row != iwin) *reinterpret_cast<uint4*>(P.out + (size_t)(rb * 128 + wrow0 + row) * DM + cj * 128 + ch * 8) = v;
      }
    }
    asm volatile("cp.async.bulk.wait_group.read 0;" ::: "memory");
    PROF(8, ct == PT, 11); STAMP(15);
    cluster_wait();
  }
}

typedef CUresult (*EncodeFn)(CUtensorMap*, CUtensorMapDataType, cuuint32_t, void*, const cuuint64_t*, const cuuint64_t*,
                             const cuuint32_t*, const cuuint32_t*, CUtensorMapInterleave, CUtensorMapSwizzle,
                             CUtensorMapL2promotion, CUtensorMapFloatOOBfill);

void map2d(EncodeFn enc, CUtensorMap* m, const void* p, uint64_t rows, uint64_t cols, uint32_t brows) {
  cuuint64_t dims[2] = {cols, rows}, strides[1] = {cols * 2};
  cuuint32_t box[2] = {64, brows}, es[2] = {1, 1};
  enc(m, CU_TENSOR_MAP_DATA_TYPE_BFLOAT16, 2, const_cast<void*>(p), dims, strides, box, es, CU_TENSOR_MAP_INTERLEAVE_NONE,
      CU_TENSOR_MAP_SWIZZLE_128B, CU_TENSOR_MAP_L2_PROMOTION_L2_256B, CU_TENSOR_MAP_FLOAT_OOB_FILL_NONE);
}
void map2d_narrow(EncodeFn enc, CUtensorMap* m, const void* p, uint64_t rows, uint64_t cols, uint32_t brows) {
  cuuint64_t dims[2] = {cols, rows}, strides[1] = {cols * 2};
  cuuint32_t box[2] = {32, brows}, es[2] = {1, 1};
  enc(m, CU_TENSOR_MAP_DATA_TYPE_BFLOAT16, 2, const_cast<void*>(p), dims, strides, box, es, CU_TENSOR_MAP_INTERLEAVE_NONE,
      CU_TENSOR_MAP_SWIZZLE_64B, CU_TENSOR_MAP_L2_PROMOTION_L2_64B, CU_TENSOR_MAP_FLOAT_OOB_FILL_NONE);
}
void map3d(EncodeFn enc, CUtensorMap* m, const void* p, uint64_t rows, uint64_t cols, uint32_t brows, uint32_t nch) {
  cuuint64_t dims[3] = {64, rows, cols / 64}, strides[2] = {cols * 2, 128};
  cuuint32_t box[3] = {64, brows, nch}, es[3] = {1, 1, 1};
  enc(m, CU_TENSOR_MAP_DATA_TYPE_BFLOAT16, 3, const_cast<void*>(p), dims, strides, box, es, CU_TENSOR_MAP_INTERLEAVE_NONE,
      CU_TENSOR_MAP_SWIZZLE_128B, CU_TENSOR_MAP_L2_PROMOTION_L2_256B, CU_TENSOR_MAP_FLOAT_OOB_FILL_NONE);
}

}

extern "C" void kernel_launch(void* const* d_in, const int* in_sizes, int n_in, void* d_out, int out_size) {
  (void)in_sizes; (void)n_in; (void)out_size;
  static EncodeFn enc = nullptr;
  if (!enc) {
    void* fn = nullptr;
    cudaDriverEntryPointQueryResult st;
    cudaGetDriverEntryPoint("cuTensorMapEncodeTiled", &fn, cudaEnableDefault, &st);
    enc = (EncodeFn)fn;
    cudaFuncSetAttribute(fused_kernel, cudaFuncAttributeMaxDynamicSharedMemorySize, SMEM_BYTES);
  }
  Maps maps;
  map2d(enc, &maps.x, d_in[0], SEQ, DM, 128);
  map2d(enc, &maps.out, d_out, SEQ, DM, 16);
  map3d(enc, &maps.wq, d_in[3], DM, NQ, 64, 2);
  map3d(enc, &maps.k, d_in[1], 4 * SK, 128, 128, 1);
  map3d(enc, &maps.v, d_in[2], 4 * SK, 128, 128, 1);
  map3d(enc, &maps.wo, d_in[4], NQ, DM, 64, 2);
  map2d_narrow(enc, &maps.wg, d_in[7], DM, FF, 256);
  map2d_narrow(enc, &maps.wu, d_in[8], DM, FF, 256);
  map3d(enc, &maps.wd, d_in[9], FF, DM, 32, 4);
  map2d_narrow(enc, &maps.wm, d_in[11], DM, NMOD, 256);
  Ptrs p;
  p.x = (const __nv_bfloat16*)d_in[0];
  p.w_r = (const __nv_bfloat16*)d_in[6];
  p.w_gate = (const __nv_bfloat16*)d_in[7];
  p.w_up = (const __nv_bfloat16*)d_in[8];
  p.w_down = (const __nv_bfloat16*)d_in[9];
  p.c = (const __nv_bfloat16*)d_in[10];
  p.w_mod = (const __nv_bfloat16*)d_in[11];
  p.out = (__nv_bfloat16*)d_out;
  fused_kernel<<<NMAIN + NHELP, 384, SMEM_BYTES>>>(maps, p);
}
```

```cpp
#include <cuda_runtime.h>
#include <cuda_bf16.h>
#include <cuda.h>
#include <stdint.h>
#include <type_traits>

#define HD 2
#define HDX 2
#define XF 4
#define XE 32
#define XR 0
#define NRS 8
#define FPACE 3
#define GOST 20
#define WB 3
#define WN 24
#define RES0 17
#define RES1 20
#define HU 32
#define NS1 6
#define PG0 0
#define PSL 0
#define CWM 7
#define WDE 16
#define CWL 1
#define CW0 0
#define ESV 1
#define PPOS 1
#define FB0 0
#define FB2 8
#define OPS 8192
#define OFL 0
#define ODS 8
#define MODUL hfma2
#define ODS1 5
#define VREL 5
#define E0 3

namespace {

constexpr int SEQ = 2048, DM = 1024, NQ = 4096, SK = 2048, WIN = 512, FF = 3584, NMOD = 6144;
constexpr int NMAIN = 128, NHELP = 4, NFFN = 112;
constexpr int NSLOT = 4, SLOT_BYTES = 32768, UNIT = 16384, GST_BYTES = 3 * UNIT;
constexpr uint32_t XT1 = 0xDCBA, XT2 = 0x9687;
constexpr uint32_t WT0 = 0xA741, WT1 = 0x7420, WT2 = 0x4A20;
constexpr uint32_t AT0 = WT1, AT1 = WT2;
constexpr uint32_t QT = 0xDC9696DC;
constexpr int OFF_STAGE = 12 * UNIT;
constexpr uint32_t FT_G = 0x07B3, FT_U = 0xA628, FT_D = 0x5149;
constexpr int OFF_RES = 12 * UNIT;
constexpr int OFF_PAR = 14 * UNIT;
constexpr int OFF_BAR = OFF_PAR + 2528;
constexpr int SMEM_BYTES = OFF_BAR + 544;
static_assert(SMEM_BYTES <= 232448, "smem");

constexpr int PAR_T1 = 0;
constexpr int PAR_T2 = 512;
constexpr int PAR_CONST = 1536;
constexpr int PAR_RED = 1600;
constexpr int PAR_SINK = 2176;

struct Maps {
  CUtensorMap x, wq, k, v, wo, wg, wu, wd, wm, out;
};
struct Ptrs {
  const __nv_bfloat16 *x, *w_r, *c, *w_mod, *w_gate, *w_up, *w_down;
  __nv_bfloat16* out;
};

__device__ __align__(1024) uint8_t g_act[16 * 80 * UNIT];
__device__ __align__(128) uint32_t g_mod[NMOD];
__device__ __align__(128) uint32_t g_modp[2 * 2 * DM];
__device__ __align__(128) uint32_t g_ln1[SEQ * 4];
__device__ __align__(128) uint32_t g_cnt_h[16 * 32];
__device__ __align__(128) uint32_t g_cnt_o[128 * 32];
__device__ __align__(128) uint32_t g_xch[NMAIN * 8 * 256 * 4];
__device__ __align__(128) uint32_t g_stats[8 * SEQ * 4];
__device__ __align__(128) uint32_t g_cand[32];
__device__ __align__(128) uint32_t g_row[16 * 2 * DM];
__device__ __align__(128) uint32_t g_ypart[NMAIN * NFFN * 8];
__device__ uint32_t g_epoch;

__device__ __forceinline__ uint32_t fresh_lane() { uint32_t l; asm volatile("mov.u32 %0, %%laneid;" : "=r"(l)); return l; }
__device__ __forceinline__ uint32_t frag_offset(int warp) {
  const uint32_t l = fresh_lane();
  return ((warp & 3) * 16 + (l & 15)) * 128 + (((l >> 4) ^ (l & 7)) << 4);
}
__device__ __forceinline__ bool elect_one() {
  uint32_t p;
  asm volatile("{ .reg .pred q; elect.sync _|q, 0xffffffff; selp.u32 %0, 1, 0, q; }" : "=r"(p));
  return p;
}
__device__ __forceinline__ uint32_t smem_u32(const void* p) { return (uint32_t)__cvta_generic_to_shared(p); }
__device__ __forceinline__ void mbar_init(uint32_t bar, uint32_t cnt) {
  asm volatile("mbarrier.init.shared::cta.b64 [%0], %1;" ::"r"(bar), "r"(cnt) : "memory");
}
__device__ __forceinline__ void mbar_expect_tx(uint32_t bar, uint32_t bytes) {
  asm volatile("mbarrier.arrive.expect_tx.shared::cta.b64 _, [%0], %1;" ::"r"(bar), "r"(bytes) : "memory");
}
__device__ __forceinline__ void mbar_arrive(uint32_t bar) {
  asm volatile("mbarrier.arrive.shared::cta.b64 _, [%0];" ::"r"(bar) : "memory");
}
__device__ __forceinline__ void mbar_arrive_pred(uint32_t bar, bool p) {
  asm volatile("{ .reg .pred p; setp.ne.b32 p, %1, 0; @p mbarrier.arrive.shared::cta.b64 _, [%0]; }" ::"r"(bar), "r"((int)p) : "memory");
}
__device__ __forceinline__ void mbar_arrive_cl(uint32_t bar, uint32_t off, bool p = true) {
  asm volatile("{ .reg .pred p, q; .reg .b32 a; setp.ne.b32 q, %2, 0; setp.ne.and.b32 p, %0, 0, q; add.u32 a, %0, %1; @p mbarrier.arrive.shared::cluster.b64 _, [a]; }"
               ::"r"(bar), "r"(off), "r"((int)p) : "memory");
}
__device__ __forceinline__ uint32_t mapa(uint32_t addr, uint32_t cta) {
  uint32_t r; asm("mapa.shared::cluster.u32 %0, %1, %2;" : "=r"(r) : "r"(addr), "r"(cta)); return r;
}
__device__ __forceinline__ void cluster_arrive() { asm volatile("barrier.cluster.arrive.relaxed.aligned;" ::: "memory"); }
__device__ __forceinline__ void cluster_wait() { asm volatile("barrier.cluster.wait.aligned;" ::: "memory"); }
__device__ __forceinline__ void watchdog(uint32_t& n) {
}
__device__ __forceinline__ void mbar_wait(uint32_t bar, uint32_t parity) {
  asm volatile("{\n.reg .pred p;\nWAIT_%=:\nmbarrier.try_wait.parity.shared::cta.b64 p, [%0], %1;\n@!p bra WAIT_%=;\n}" ::"r"(bar), "r"(parity) : "memory");
}
__device__ __forceinline__ bool mbar_test(uint32_t bar, uint32_t parity) {
  uint32_t ok;
  asm volatile("{\n.reg .pred p;\nmbarrier.test_wait.parity.shared::cta.b64 p, [%1], %2;\nselp.u32 %0, 1, 0, p;\n}" : "=r"(ok) : "r"(bar), "r"(parity) : "memory");
  return ok;
}
__device__ __forceinline__ uint64_t l2_stream() {
  uint64_t f; asm("createpolicy.fractional.L2::evict_first.b64 %0, 1.0;" : "=l"(f)); return f;
}
__device__ __forceinline__ void tma2d(uint32_t dst, const CUtensorMap* m, int c0, int c1, uint32_t bar) {
  asm volatile("cp.async.bulk.tensor.2d.shared::cluster.global.mbarrier::complete_tx::bytes.L2::cache_hint [%0], [%1, {%3, %4}], [%2], %5;"
               ::"r"(dst), "l"(m), "r"(bar), "r"(c0), "r"(c1), "l"(l2_stream()) : "memory");
}
__device__ __forceinline__ void bulk_load(uint32_t dst, const void* src, uint32_t bytes, uint32_t bar) {
  asm volatile("cp.async.bulk.shared::cluster.global.mbarrier::complete_tx::bytes [%0], [%1], %2, [%3];" ::"r"(dst), "l"(src), "r"(bytes), "r"(bar) : "memory");
}
__device__ __forceinline__ void bulk_load_stream(uint32_t dst, const void* src, uint32_t bytes, uint32_t bar) {
  asm volatile("cp.async.bulk.shared::cluster.global.mbarrier::complete_tx::bytes.L2::cache_hint [%0], [%1], %2, [%3], %4;"
               ::"r"(dst), "l"(src), "r"(bytes), "r"(bar), "l"(l2_stream()) : "memory");
}
__device__ __forceinline__ void tma2d_store(const CUtensorMap* m, uint32_t src, int c0, int c1) {
  asm volatile("cp.async.bulk.tensor.2d.global.shared::cta.bulk_group [%0, {%2, %3}], [%1];" ::"l"(m), "r"(src), "r"(c0), "r"(c1) : "memory");
}
__device__ __forceinline__ void bulk_store(void* dst, uint32_t src, uint32_t bytes) {
  asm volatile("cp.async.bulk.global.shared::cta.bulk_group [%0], [%1], %2;" ::"l"(dst), "r"(src), "r"(bytes) : "memory");
}
__device__ __forceinline__ uint32_t unit_of(uint32_t table, uint32_t i) { return ((table >> (i * 4)) & 15) * UNIT; }
__device__ __forceinline__ void tma3d(uint32_t dst, const CUtensorMap* m, int c0, int c1, int c2, uint32_t bar) {
  asm volatile("cp.async.bulk.tensor.3d.shared::cluster.global.mbarrier::complete_tx::bytes.L2::cache_hint [%0], [%1, {%3, %4, %5}], [%2], %6;"
               ::"r"(dst), "l"(m), "r"(bar), "r"(c0), "r"(c1), "r"(c2), "l"(l2_stream()) : "memory");
}
template <bool STREAM>
__device__ __forceinline__ void tma3d_mc(uint32_t dst, const CUtensorMap* m, int c0, int c1, int c2, uint32_t bar) {
  if (STREAM)
    asm volatile("cp.async.bulk.tensor.3d.shared::cluster.global.mbarrier::complete_tx::bytes.multicast::cluster.L2::cache_hint [%0], [%1, {%3, %4, %5}], [%2], %6, %7;"
                 ::"r"(dst), "l"(m), "r"(bar), "r"(c0), "r"(c1), "r"(c2), "h"((uint16_t)3), "l"(l2_stream()) : "memory");
  else
    asm volatile("cp.async.bulk.tensor.3d.shared::cluster.global.mbarrier::complete_tx::bytes.multicast::cluster [%0], [%1, {%3, %4, %5}], [%2], %6;"
                 ::"r"(dst), "l"(m), "r"(bar), "r"(c0), "r"(c1), "r"(c2), "h"((uint16_t)3) : "memory");
}
__device__ __forceinline__ void prefetch_map(const CUtensorMap* m) {
  asm volatile("prefetch.tensormap [%0];" ::"l"(m) : "memory");
}
__device__ __forceinline__ void fence_async() { asm volatile("fence.proxy.async.global;" ::: "memory"); }
__device__ __forceinline__ void fence_async_smem() { asm volatile("fence.proxy.async.shared::cta;" ::: "memory"); }
__device__ __forceinline__ void bar_sync(int id, int n) { asm volatile("bar.sync %0, %1;" ::"r"(id), "r"(n) : "memory"); }
__device__ __forceinline__ void bar_arrive(int id, int n) { asm volatile("bar.arrive %0, %1;" ::"r"(id), "r"(n) : "memory"); }
__device__ __forceinline__ void wg_fence() { asm volatile("wgmma.fence.sync.aligned;" ::: "memory"); }
__device__ __forceinline__ void wg_commit() { asm volatile("wgmma.commit_group.sync.aligned;" ::: "memory"); }
template <int N> __device__ __forceinline__ void wg_wait() { asm volatile("wgmma.wait_group.sync.aligned %0;" ::"n"(N) : "memory"); }
__device__ __forceinline__ uint64_t make_desc(uint32_t addr, uint32_t lbo, uint32_t sbo) {
  return (uint64_t)((addr & 0x3FFFF) >> 4) | ((uint64_t)(lbo >> 4) << 16) | ((uint64_t)(sbo >> 4) << 32) | (1ull << 62);
}
__device__ __forceinline__ uint32_t ld_relaxed(const uint32_t* p) {
  uint32_t v; asm volatile("ld.relaxed.gpu.global.u32 %0, [%1];" : "=r"(v) : "l"(p) : "memory"); return v;
}
__device__ __forceinline__ uint32_t ld_acquire(const uint32_t* p) {
  uint32_t v; asm volatile("ld.acquire.gpu.global.u32 %0, [%1];" : "=r"(v) : "l"(p) : "memory"); return v;
}
__device__ __forceinline__ uint4 ld_relaxed4(const uint32_t* p) {
  uint4 v; asm volatile("ld.relaxed.gpu.global.v4.u32 {%0,%1,%2,%3}, [%4];" : "=r"(v.x), "=r"(v.y), "=r"(v.z), "=r"(v.w) : "l"(p) : "memory"); return v;
}
__device__ __forceinline__ uint2 ld_relaxed2(const uint32_t* p) {
  uint2 v; asm volatile("ld.relaxed.gpu.global.v2.u32 {%0,%1}, [%2];" : "=r"(v.x), "=r"(v.y) : "l"(p) : "memory"); return v;
}
__device__ __forceinline__ void st_relaxed(uint32_t* p, uint32_t v) {
  asm volatile("st.relaxed.gpu.global.u32 [%0], %1;" ::"l"(p), "r"(v) : "memory");
}
__device__ __forceinline__ void st_relaxed2(uint32_t* p, uint32_t a, uint32_t b) {
  asm volatile("st.relaxed.gpu.global.v2.u32 [%0], {%1,%2};" ::"l"(p), "r"(a), "r"(b) : "memory");
}
__device__ __forceinline__ void st_relaxed4(uint32_t* p, uint32_t a, uint32_t b, uint32_t c, uint32_t d) {
  asm volatile("st.relaxed.gpu.global.v4.u32 [%0], {%1,%2,%3,%4};" ::"l"(p), "r"(a), "r"(b), "r"(c), "r"(d) : "memory");
}
__device__ __forceinline__ void st_b128(uint32_t* p, uint32_t a, uint32_t b, uint32_t c, uint32_t d) {
  asm volatile("{ .reg .b64 u, v; .reg .b128 w; mov.b64 u, {%1, %2}; mov.b64 v, {%3, %4}; mov.b128 w, {u, v}; st.relaxed.gpu.global.b128 [%0], w; }"
               ::"l"(p), "r"(a), "r"(b), "r"(c), "r"(d) : "memory");
}
__device__ __forceinline__ uint4 ld_b128(const uint32_t* p) {
  uint4 r;
  asm volatile("{ .reg .b64 u, v; .reg .b128 w; ld.relaxed.gpu.global.b128 w, [%4]; mov.b128 {u, v}, w; mov.b64 {%0, %1}, u; mov.b64 {%2, %3}, v; }"
               : "=r"(r.x), "=r"(r.y), "=r"(r.z), "=r"(r.w) : "l"(p) : "memory");
  return r;
}
__device__ __forceinline__ void st_pairs(uint32_t* p, uint32_t a, uint32_t b, uint32_t tag) {
  asm volatile("{ .reg .b64 u, v; mov.b64 u, {%1, %3}; mov.b64 v, {%2, %3}; st.relaxed.gpu.global.v2.b64 [%0], {u, v}; }"
               ::"l"(p), "r"(a), "r"(b), "r"(tag) : "memory");
}
__device__ __forceinline__ uint4 ld_pairs(const uint32_t* p) {
  uint4 v;
  asm volatile("{ .reg .b64 u, v; ld.relaxed.gpu.global.v2.b64 {u, v}, [%4]; mov.b64 {%0, %1}, u; mov.b64 {%2, %3}, v; }"
               : "=r"(v.x), "=r"(v.y), "=r"(v.z), "=r"(v.w) : "l"(p) : "memory");
  return v;
}
__device__ __forceinline__ uint2 ld_pair(const uint32_t* p) {
  uint2 v;
  asm volatile("{ .reg .b64 u; ld.relaxed.gpu.global.b64 u, [%2]; mov.b64 {%0, %1}, u; }" : "=r"(v.x), "=r"(v.y) : "l"(p) : "memory");
  return v;
}
__device__ __forceinline__ void red_release(uint32_t* p, uint32_t v) {
  asm volatile("red.release.gpu.global.add.u32 [%0], %1;" ::"l"(p), "r"(v) : "memory");
}
__device__ __forceinline__ uint32_t ldg_nc1(const void* p) {
  uint32_t v;
  asm volatile("ld.global.nc.u32 %0, [%1];" : "=r"(v) : "l"(p));
  return v;
}
__device__ __forceinline__ uint4 ldg_nc4(const void* p) {
  uint4 v; asm volatile("ld.global.nc.L1::no_allocate.v4.u32 {%0,%1,%2,%3}, [%4];" : "=r"(v.x), "=r"(v.y), "=r"(v.z), "=r"(v.w) : "l"(p)); return v;
}
__device__ __forceinline__ uint4 ldg_stream4(const void* p) {
  uint4 v;
  asm volatile("ld.global.nc.L1::no_allocate.L2::cache_hint.v4.u32 {%0,%1,%2,%3}, [%4], %5;" : "=r"(v.x), "=r"(v.y), "=r"(v.z), "=r"(v.w) : "l"(p), "l"(l2_stream()));
  return v;
}
__device__ __forceinline__ void stg4(void* p, uint4 v) {
  asm volatile("st.global.v4.u32 [%0], {%1,%2,%3,%4};" ::"l"(p), "r"(v.x), "r"(v.y), "r"(v.z), "r"(v.w) : "memory");
}
__device__ __forceinline__ void wait_counter(const uint32_t* p, uint32_t target) {
  uint32_t n = 0;
  while (__any_sync(0xffffffffu, (int)(ld_acquire(p) - target) < 0)) { watchdog(n); }
}
__device__ __forceinline__ uint32_t tagf(float v, uint32_t tag) { return (__float_as_uint(v) & ~3u) | tag; }
__device__ __forceinline__ bool tag_ok(uint4 v, uint32_t tag) { return (((v.x ^ tag) | (v.y ^ tag) | (v.z ^ tag) | (v.w ^ tag)) & 3u) == 0; }
__device__ __forceinline__ float untag_sum(uint32_t a, uint32_t b) { return __uint_as_float(a & ~3u) + __uint_as_float(b & ~3u); }
__device__ __forceinline__ uint4 poll4(const uint32_t* p, uint32_t tag) {
  uint4 v = ld_relaxed4(p);
  uint32_t n = 0;
  while (!__all_sync(0xffffffffu, tag_ok(v, tag))) { v = ld_relaxed4(p); watchdog(n); }
  return v;
}
__device__ __forceinline__ float bf_lo(uint32_t v) { return __uint_as_float(v << 16); }
__device__ __forceinline__ float bf_hi(uint32_t v) { return __uint_as_float(v & 0xffff0000u); }
__device__ __forceinline__ uint32_t pack_bf(float lo, float hi) {
  uint32_t r; asm("cvt.rn.bf16x2.f32 %0, %1, %2;" : "=r"(r) : "f"(hi), "f"(lo)); return r;
}
__device__ __forceinline__ float rbf(float v) { return __uint_as_float(pack_bf(0.f, v) & 0xffff0000u); }
__device__ __forceinline__ uint32_t hmul2(uint32_t a, uint32_t b) {
  uint32_t r; asm("mul.rn.bf16x2 %0, %1, %2;" : "=r"(r) : "r"(a), "r"(b)); return r;
}
__device__ __forceinline__ uint32_t hadd2(uint32_t a, uint32_t b) {
  uint32_t r; asm("add.rn.bf16x2 %0, %1, %2;" : "=r"(r) : "r"(a), "r"(b)); return r;
}
__device__ __forceinline__ uint32_t hsub2(uint32_t a, uint32_t b) {
  uint32_t r; asm("sub.rn.bf16x2 %0, %1, %2;" : "=r"(r) : "r"(a), "r"(b)); return r;
}
__device__ __forceinline__ uint32_t hmax2(uint32_t a, uint32_t b) {
  uint32_t r; asm("max.bf16x2 %0, %1, %2;" : "=r"(r) : "r"(a), "r"(b)); return r;
}
__device__ __forceinline__ float rcp(float x) { float r; asm("rcp.approx.ftz.f32 %0, %1;" : "=f"(r) : "f"(x)); return r; }
__device__ __forceinline__ float ex2(float x) { float r; asm("ex2.approx.ftz.f32 %0, %1;" : "=f"(r) : "f"(x)); return r; }
__device__ __forceinline__ void stmatrix4(uint32_t addr, uint32_t a, uint32_t b, uint32_t c, uint32_t d) {
  asm volatile("stmatrix.sync.aligned.m8n8.x4.shared.b16 [%0], {%1,%2,%3,%4};" ::"r"(addr), "r"(a), "r"(b), "r"(c), "r"(d) : "memory");
}
__device__ __forceinline__ void ldmatrix4(uint32_t addr, uint32_t& a, uint32_t& b, uint32_t& c, uint32_t& d) {
  asm volatile("ldmatrix.sync.aligned.m8n8.x4.shared.b16 {%0,%1,%2,%3}, [%4];" : "=r"(a), "=r"(b), "=r"(c), "=r"(d) : "r"(addr) : "memory");
}
__device__ __forceinline__ void ldmatrix4t(uint32_t addr, uint32_t& a, uint32_t& b, uint32_t& c, uint32_t& d) {
  asm volatile("ldmatrix.sync.aligned.m8n8.x4.trans.shared.b16 {%0,%1,%2,%3}, [%4];" : "=r"(a), "=r"(b), "=r"(c), "=r"(d) : "r"(addr) : "memory");
}
__device__ __forceinline__ void mma16816(float (&d)[4], uint32_t a0, uint32_t a1, uint32_t a2, uint32_t a3, uint32_t b0, uint32_t b1) {
  asm volatile("mma.sync.aligned.m16n8k16.row.col.f32.bf16.bf16.f32 {%0,%1,%2,%3}, {%4,%5,%6,%7}, {%8,%9}, {%0,%1,%2,%3};"
               : "+f"(d[0]), "+f"(d[1]), "+f"(d[2]), "+f"(d[3]) : "r"(a0), "r"(a1), "r"(a2), "r"(a3), "r"(b0), "r"(b1));
}
__device__ __forceinline__ void sts1(uint32_t a, uint32_t v) { asm volatile("st.shared.u32 [%0], %1;" ::"r"(a), "r"(v) : "memory"); }
__device__ __forceinline__ uint4 lds4(uint32_t a) {
  uint4 v; asm volatile("ld.shared.v4.u32 {%0,%1,%2,%3}, [%4];" : "=r"(v.x), "=r"(v.y), "=r"(v.z), "=r"(v.w) : "r"(a) : "memory"); return v;
}
__device__ __forceinline__ uint2 lds2(uint32_t a) {
  uint2 v; asm volatile("ld.shared.v2.u32 {%0,%1}, [%2];" : "=r"(v.x), "=r"(v.y) : "r"(a) : "memory"); return v;
}
__device__ __forceinline__ uint32_t lds1(uint32_t a) {
  uint32_t v; asm volatile("ld.shared.u32 %0, [%1];" : "=r"(v) : "r"(a) : "memory"); return v;
}
__device__ __forceinline__ void sts2(uint32_t a, uint32_t x, uint32_t y) { asm volatile("st.shared.v2.u32 [%0], {%1,%2};" ::"r"(a), "r"(x), "r"(y) : "memory"); }
__device__ __forceinline__ void sts4(uint32_t a, uint4 v) {
  asm volatile("st.shared.v4.u32 [%0], {%1,%2,%3,%4};" ::"r"(a), "r"(v.x), "r"(v.y), "r"(v.z), "r"(v.w) : "memory");
}
__device__ __forceinline__ float silu_f(float v) { return __fdividef(v, 1.f + __expf(-v)); }
__device__ __forceinline__ uint32_t hfma2(uint32_t a, uint32_t b, uint32_t c) {
  uint32_t r; asm("fma.rn.bf16x2 %0, %1, %2, %3;" : "=r"(r) : "r"(a), "r"(b), "r"(c)); return r;
}
__device__ __forceinline__ void split_inv(float sd, uint32_t& ih, uint32_t& il) {
  const float inv = rcp(sd);
  ih = pack_bf(inv, inv);
  const float lo = inv - bf_lo(ih);
  il = pack_bf(lo, lo);
}
__device__ __forceinline__ uint32_t ln_norm(uint32_t x, uint32_t mean2, uint32_t ih, uint32_t il) {
  const uint32_t d = hsub2(x, mean2);
  return hfma2(d, ih, hmul2(d, il));
}
__device__ __forceinline__ uint32_t modul(uint32_t n, uint32_t c1, uint32_t sh) { return hadd2(hmul2(n, c1), sh); }
__device__ __forceinline__ uint32_t ln_mod(uint32_t x, uint32_t mean2, uint32_t ih, uint32_t il, uint32_t c1, uint32_t sh) {
  return modul(ln_norm(x, mean2, ih, il), c1, sh);
}

#define R8(a, i) "+f"(a[i]), "+f"(a[i + 1]), "+f"(a[i + 2]), "+f"(a[i + 3]), "+f"(a[i + 4]), "+f"(a[i + 5]), "+f"(a[i + 6]), "+f"(a[i + 7])
#define D64 "{%0,%1,%2,%3,%4,%5,%6,%7,%8,%9,%10,%11,%12,%13,%14,%15,%16,%17,%18,%19,%20,%21,%22,%23,%24,%25,%26,%27,%28,%29,%30,%31," \
            "%32,%33,%34,%35,%36,%37,%38,%39,%40,%41,%42,%43,%44,%45,%46,%47,%48,%49,%50,%51,%52,%53,%54,%55,%56,%57,%58,%59,%60,%61,%62,%63}"
template <int TB>
__device__ __forceinline__ void mma_ss(float (&d)[64], uint64_t da, uint64_t db, int sc) {
  asm volatile("{\n.reg .pred p;\nsetp.ne.b32 p, %66, 0;\n"
               "wgmma.mma_async.sync.aligned.m64n128k16.f32.bf16.bf16 " D64 ", %64, %65, p, 1, 1, 0, %67;\n}"
               : R8(d, 0), R8(d, 8), R8(d, 16), R8(d, 24), R8(d, 32), R8(d, 40), R8(d, 48), R8(d, 56)
               : "l"(da), "l"(db), "r"(sc), "n"(TB));
}
template <int TB>
__device__ __forceinline__ void mma_rs(float (&d)[64], uint32_t a0, uint32_t a1, uint32_t a2, uint32_t a3, uint64_t db, int sc) {
  asm volatile("{\n.reg .pred p;\nsetp.ne.b32 p, %69, 0;\n"
               "wgmma.mma_async.sync.aligned.m64n128k16.f32.bf16.bf16 " D64 ", {%64,%65,%66,%67}, %68, p, 1, 1, %70;\n}"
               : R8(d, 0), R8(d, 8), R8(d, 16), R8(d, 24), R8(d, 32), R8(d, 40), R8(d, 48), R8(d, 56)
               : "r"(a0), "r"(a1), "r"(a2), "r"(a3), "l"(db), "r"(sc), "n"(TB));
}
#define D128 "{%0,%1,%2,%3,%4,%5,%6,%7,%8,%9,%10,%11,%12,%13,%14,%15,%16,%17,%18,%19,%20,%21,%22,%23,%24,%25,%26,%27,%28,%29,%30,%31," \
             "%32,%33,%34,%35,%36,%37,%38,%39,%40,%41,%42,%43,%44,%45,%46,%47,%48,%49,%50,%51,%52,%53,%54,%55,%56,%57,%58,%59,%60,%61,%62,%63," \
             "%64,%65,%66,%67,%68,%69,%70,%71,%72,%73,%74,%75,%76,%77,%78,%79,%80,%81,%82,%83,%84,%85,%86,%87,%88,%89,%90,%91,%92,%93,%94,%95," \
             "%96,%97,%98,%99,%100,%101,%102,%103,%104,%105,%106,%107,%108,%109,%110,%111,%112,%113,%114,%115,%116,%117,%118,%119,%120,%121,%122,%123,%124,%125,%126,%127}"
#define R128(d, e) R8(d, 0), R8(d, 8), R8(d, 16), R8(d, 24), R8(d, 32), R8(d, 40), R8(d, 48), R8(d, 56), \
                   R8(e, 0), R8(e, 8), R8(e, 16), R8(e, 24), R8(e, 32), R8(e, 40), R8(e, 48), R8(e, 56)
__device__ __forceinline__ void mma256_ss(float (&d)[64], float (&e)[64], uint64_t da, uint64_t db, int sc) {
  asm volatile("{\n.reg .pred p;\nsetp.ne.b32 p, %130, 0;\n"
               "wgmma.mma_async.sync.aligned.m64n256k16.f32.bf16.bf16 " D128 ", %128, %129, p, 1, 1, 0, 1;\n}"
               : R128(d, e) : "l"(da), "l"(db), "r"(sc));
}
__device__ __forceinline__ void mma256_rs(float (&d)[64], float (&e)[64], uint32_t a0, uint32_t a1, uint32_t a2, uint32_t a3, uint64_t db) {
  asm volatile("{\n.reg .pred p;\nsetp.ne.b32 p, 1, 0;\n"
               "wgmma.mma_async.sync.aligned.m64n256k16.f32.bf16.bf16 " D128 ", {%128,%129,%130,%131}, %132, p, 1, 1, 1;\n}"
               : R128(d, e) : "r"(a0), "r"(a1), "r"(a2), "r"(a3), "l"(db));
}
template <int N> __device__ __forceinline__ void keep(float (&a)[N]) {
#pragma unroll
  for (int i = 0; i < N; i++) asm volatile("" : "+f"(a[i])::"memory");
}
template <int N> __device__ __forceinline__ void keep(uint32_t (&a)[N]) {
#pragma unroll
  for (int i = 0; i < N; i++) asm volatile("" : "+r"(a[i])::"memory");
}

#define STAMP(idx) do {} while (0)
#define PROF(grp, cond, idx) do {} while (0)

constexpr float SCL2 = 1.4426950408889634f * 0.08838834764831845f;

__device__ __forceinline__ void pack_p(const float (&s)[64], uint32_t (&p)[32]) {
#pragma unroll
  for (int i = 0; i < 32; i++) p[i] = pack_bf(s[2 * i], s[2 * i + 1]);
}

__device__ __forceinline__ void issue_qk(float (&s)[64], uint32_t q0, uint32_t q1, uint32_t kslot) {
  const uint64_t db = make_desc(kslot, 16, 1024), da0 = make_desc(q0, 16, 1024), da1 = make_desc(q1, 16, 1024);
#pragma unroll
  for (int kk = 0; kk < 8; kk++) mma_ss<0>(s, (kk < 4 ? da0 : da1) + (kk & 3) * 2, db + (kk >> 2) * 1024 + (kk & 3) * 2, kk != 0);
}
__device__ __forceinline__ void issue_pv(float (&o)[64], uint32_t (&p)[32], uint32_t vslot, int acc) {
  uint64_t db = make_desc(vslot, 16384, 1024);
#pragma unroll
  for (int kk = 0; kk < 8; kk++)
    mma_rs<1>(o, p[4 * kk], p[4 * kk + 1], p[4 * kk + 2], p[4 * kk + 3], db + kk * 128, kk == 0 ? acc : 1);
}

template <int H>
__device__ __forceinline__ void store_chunk(const float (&a)[64], uint32_t addr) {
#pragma unroll
  for (int i = 8 * H; i < 8 * H + 8; i += 2)
    stmatrix4(addr ^ ((i & 7) << 4), pack_bf(a[4 * i], a[4 * i + 1]), pack_bf(a[4 * i + 2], a[4 * i + 3]),
              pack_bf(a[4 * i + 4], a[4 * i + 5]), pack_bf(a[4 * i + 6], a[4 * i + 7]));
}
template <int H>
__device__ __forceinline__ void store_chunk(const float (&a)[64], float i0, float i1, uint32_t addr) {
#pragma unroll
  for (int i = 8 * H; i < 8 * H + 8; i += 2)
    stmatrix4(addr ^ ((i & 7) << 4), pack_bf(a[4 * i] * i0, a[4 * i + 1] * i0), pack_bf(a[4 * i + 2] * i1, a[4 * i + 3] * i1),
              pack_bf(a[4 * i + 4] * i0, a[4 * i + 5] * i0), pack_bf(a[4 * i + 6] * i1, a[4 * i + 7] * i1));
}
__device__ __forceinline__ float inv_quad_sum(float l) {
  l += __shfl_xor_sync(0xffffffffu, l, 1);
  l += __shfl_xor_sync(0xffffffffu, l, 2);
  return rcp(l);
}

__device__ __forceinline__ void ln_scalars(float mean, float var, float& mb, float& sd) {
  mb = rbf(mean);
  float r; asm("sqrt.approx.ftz.f32 %0, %1;" : "=f"(r) : "f"(rbf(rbf(var) + 1e-5f)));
  sd = rbf(r);
}

__global__ void __cluster_dims__(2, 1, 1) __launch_bounds__(384, 1) fused_kernel(const __grid_constant__ Maps maps, const Ptrs P) {
  extern __shared__ __align__(1024) uint8_t smem_raw[];
  const uint32_t base = smem_u32(smem_raw);
  const int tid = threadIdx.x, lane = tid & 31;
  const int warp = __shfl_sync(0xffffffffu, tid >> 5, 0);
  const int b = blockIdx.x;
  PROF(31, tid == 0, 0);

  if (b >= NMAIN) {
    float* sc = reinterpret_cast<float*>(smem_raw);
    float* red = sc + DM;
    for (int k = tid; k < DM; k += 384) sc[k] = rbf(silu_f(__bfloat162float(P.c[k])));
    __syncthreads();
    if (tid < 256) {
      const int col = 2048 + (b - NMAIN) * 1024 + (tid & 127) * 8, r0 = (tid >> 7) * 512;
      float acc[8];
#pragma unroll
      for (int e = 0; e < 8; e++) acc[e] = 0.f;
#pragma unroll 1
      for (int r = r0; r < r0 + 512; r += HU) {
        uint4 w[HU];
#pragma unroll
        for (int u = 0; u < HU; u++) w[u] = ldg_stream4(P.w_mod + (size_t)(r + u) * NMOD + col);
#pragma unroll
        for (int u = 0; u < HU; u++) {
          float s = sc[r + u];
          acc[0] += s * bf_lo(w[u].x); acc[1] += s * bf_hi(w[u].x); acc[2] += s * bf_lo(w[u].y); acc[3] += s * bf_hi(w[u].y);
          acc[4] += s * bf_lo(w[u].z); acc[5] += s * bf_hi(w[u].z); acc[6] += s * bf_lo(w[u].w); acc[7] += s * bf_hi(w[u].w);
        }
      }
      if (tid >= 128) {
#pragma unroll
        for (int e = 0; e < 8; e++) red[(tid & 127) * 8 + e] = acc[e];
      }
      const uint32_t tag = ld_relaxed(&g_epoch) % 3 + 1;
      bar_sync(1, 256);
      if (tid < 128) {
        uint32_t o[8];
#pragma unroll
        for (int e = 0; e < 8; e++) o[e] = __float_as_uint(rbf(acc[e] + red[tid * 8 + e])) | tag;
        st_relaxed4(g_mod + col, o[0], o[1], o[2], o[3]);
        st_relaxed4(g_mod + col + 4, o[4], o[5], o[6], o[7]);
        const uint4 wr = ldg_nc4(P.w_r + tid * 8);
        const uint32_t wv[4] = {wr.x, wr.y, wr.z, wr.w};
        float dsum = 0.f;
#pragma unroll
        for (int e = 0; e < 8; e++) {
          const float m = bf_hi(o[e]);
          dsum += (b == NMAIN + 2 ? rbf(1.f + m) : m) * ((e & 1) ? bf_hi(wv[e >> 1]) : bf_lo(wv[e >> 1]));
        }
#pragma unroll
        for (int k = 16; k > 0; k >>= 1) dsum += __shfl_xor_sync(0xffffffffu, dsum, k);
        if (lane == 0) st_relaxed(g_mod + (b - NMAIN) * 4 + warp, tagf(dsum, tag));
      }
    }
    PROF(2, tid == 0, 1);
    return;
  }

  const int rank = b & 1;
  const int rb = ((b >> 4) << 1) | rank, cj = (b >> 1) & 7;
  const uint32_t bfull = base + OFF_BAR, bempty = bfull + NSLOT * 8;
  const uint32_t gfull = bempty + NSLOT * 8, gempty = gfull + 32;
  const uint32_t bar_ofull = gempty + 32;
  const uint32_t bar_ofree = bar_ofull + 32;
  const uint32_t bar_par = bar_ofree + 32;
  const uint32_t bar_mod = bar_par + 8;
  const uint32_t bar_pread = bar_mod + 8;
  const uint32_t bar_xres = bar_pread + 8;
  const uint32_t bar_ring = bar_xres + 8;
  const uint32_t bar_box = bar_ring + 24;
  const uint32_t bar_go = bar_box + 96;
  const uint32_t bar_go2 = bar_go + 16;
  const uint32_t bar_cnt = bar_go + 24;
  const uint32_t xfull = bar_go + 40, xempty = xfull + 32;
  const uint32_t bar_hw = xempty + 32, bar_hx = bar_hw + 8;
  const uint32_t bar_hpub = bar_hx + 16;
  const uint32_t bar_win = bar_hpub + 16;
  const uint32_t bar_rx = bar_win + 8;
  const uint32_t bar_sel = bar_rx + 8;
  const uint32_t bar_gate = bar_sel + 8;
  const uint32_t bar_rel = bar_gate + 8;
  const uint32_t bar_od = bar_rel + 8;
  const uint32_t bar_res = bar_go + 8;
  const uint32_t stage = base + OFF_STAGE, par = base + OFF_PAR;

  if (warp == 8 && elect_one()) {
    for (int s = 0; s < NSLOT; s++) { mbar_init(bfull + s * 8, 1); mbar_init(bempty + s * 8, 16); }
    for (int s = 0; s < 4; s++) { mbar_init(gfull + s * 8, 1); mbar_init(gempty + s * 8, 16); mbar_init(xfull + s * 8, 1); mbar_init(xempty + s * 8, 8); mbar_init(bar_ofree + s * 8, 1); mbar_init(bar_ofull + s * 8, 128); }
    mbar_init(bar_par, 64); mbar_init(bar_mod, 256); mbar_init(bar_pread, 2); mbar_init(bar_xres, 1);
    mbar_init(bar_ring, 8); mbar_init(bar_ring + 8, 8); mbar_init(bar_ring + 16, 8);
    mbar_init(bar_go, 1); mbar_init(bar_go2, 1); mbar_init(bar_cnt, 1); mbar_init(bar_cnt + 8, 1); mbar_init(bar_hpub, 8); mbar_init(bar_hpub + 8, 8); mbar_init(bar_res, 1); mbar_init(bar_win, 1); mbar_init(bar_rx, 1); mbar_init(bar_sel, 64); mbar_init(bar_gate, 8); mbar_init(bar_rel, 8); mbar_init(bar_od, 1);
    for (int s = 0; s < 12; s++) mbar_init(bar_box + s * 8, 1);
    asm volatile("fence.mbarrier_init.release.cluster;" ::: "memory");
    prefetch_map(&maps.x); prefetch_map(&maps.wq); prefetch_map(&maps.k); prefetch_map(&maps.v);
  }
  if (warp == 9 && elect_one()) {
    mbar_init(bar_hw, 1); mbar_init(bar_hx, 1); mbar_init(bar_hx + 8, 1);
    asm volatile("fence.mbarrier_init.release.cluster;" ::: "memory");
    mbar_expect_tx(bar_hw, 32768);
    mbar_expect_tx(bar_hx, 16384);
    mbar_expect_tx(bar_hx + 8, 16384);
    const __nv_bfloat16* xs = P.x + (size_t)(rb * 128 + cj * 16) * DM;
    bulk_load(base + 2 * GST_BYTES, xs, 16384, bar_hx);
    tma2d(stage, &maps.wm, (b >> 1) * 32, rank * 512, bar_hw);
    tma2d(stage + 16384, &maps.wm, (b >> 1) * 32, rank * 512 + 256, bar_hw);
    bulk_load(base + 3 * GST_BYTES, xs + 8 * DM, 16384, bar_hx + 8);
  }
  cluster_arrive();

  if (warp >= 8) {
    asm volatile("setmaxnreg.dec.sync.aligned.u32 40;");
    if (warp < 10) bar_arrive(1, 320);
    const uint32_t epoch = ld_relaxed(&g_epoch);
    cluster_wait();
    if (warp == 8) {
      const int kvrow = (cj >> 1) * SK + (SK - WIN);
      int wch = cj * 8 + rank * 2;
#pragma unroll 1
      for (int ps = 0; ps < 3; ps++) {
        const CUtensorMap* mw = ps == 2 ? &maps.wo : &maps.wq;
        const uint32_t xt = ps == 1 ? XT1 : XT2, wt = ps == 0 ? WT0 : (ps == 1 ? WT1 : WT2);
        const int nst = ps == 2 ? 32 : 16;
#pragma unroll 1
        for (int i = 0; i < nst; i++) {
          const uint32_t bf = gfull + (i & 3) * 8;
          const int kt = ps == 2 ? (((cj & 1) * 4 + ((i >> 1) & 3)) * 4 + (i >> 3)) * 2 + (i & 1) : (i + (ps ? 0 : b & 14)) & 15;
          const uint32_t wd = base + unit_of(wt, i & 3) + rank * UNIT, xd = base + unit_of(xt, i & 3);
          const uint8_t* xs = g_act + (uint32_t)(rb * 80 + (ps - 1) * 16 + kt) * UNIT;
          if (ps == 0 && i == HD) mbar_wait(bar_mod, 0);
          const bool xfirst = ps && i < 2;
          if (ps == 2 && i == 0) mbar_wait(bar_ofree + 24, 0);
          if (i == 0) fence_async();
          mbar_wait(gempty + (i & 3) * 8, ((i >> 2) & 1) ^ 1);
          if (elect_one()) {
            mbar_expect_tx(bf, ps ? GST_BYTES : 2 * UNIT);
            if (xfirst) bulk_load_stream(xd, xs, UNIT, bf);
          }
          if (ps && i < 4) mbar_wait(bempty + i * 8, 1);
          if (elect_one()) tma3d_mc<true>(wd, mw, 0, (i == 31 ? kt ^ (rank * 32) : kt) * 64, i == 31 ? cj * 2 : wch, bf);
          if (ps) {
            if (i == 16 || i == 24) { mbar_wait(bar_cnt + i - 16, 0); fence_async(); }
            if (i == RES0) mbar_wait(bar_res, 0);
            if (i == 2) mbar_wait(bar_ofree + (ps - 1) * 16, 0);
            if (elect_one()) {
              if (i == 31) bulk_load(xd, xs, UNIT, bf); else if (!xfirst) bulk_load_stream(xd, xs, UNIT, bf);
              mbar_arrive_pred(bar_go, i == GOST - 1);
              mbar_arrive_pred(bar_od, i == (ps == 1 ? ODS1 : ODS));
              if (i == RES0) mbar_expect_tx(bar_xres, 32768);
              if (i == RES0 || i == RES1) tma2d(base + OFF_RES + (i == RES1) * UNIT, &maps.x, cj * 128 + (i == RES1) * 64, rb * 128, bar_xres);
            }
          }
        }
        if (ps == 2) break;
        wch = ps ? ((wch >> 3) ^ rank) * 2 : wch + 4;
#pragma unroll 1
        for (int u = 0; u < 16; u++) {
          const bool isk = (u == 0) || ((u & 1) && u < 15);
          const int blk = (isk ? (u + 1) >> 1 : (u == 15 ? 7 : (u >> 1) - 1)) & 3;
          const uint32_t sl = base + unit_of(ps ? AT1 : AT0, u & 3) + rank * UNIT, bf = bfull + (u & 3) * 8;
          if (u < 4) mbar_wait(gempty + ((u + 1) >> 1) * 8, 1);
          mbar_wait(bempty + (u & 3) * 8, ((u >> 2) & 1) ^ 1);
          if (elect_one()) {
            mbar_arrive_pred(bar_go2, ps && u == PG0);
            mbar_expect_tx(bf, SLOT_BYTES);
            tma3d_mc<false>(sl, isk ? &maps.k : &maps.v, 0, kvrow + blk * 128, rank, bf);
          }
        }
      }
      if (elect_one()) mbar_expect_tx(bar_rx, UNIT);
      mbar_wait(bar_rel, 0);
      if (elect_one()) {
        bulk_load_stream(base + UNIT, g_act + (uint32_t)(rb * 80 + 16 + 63 - (cj & 1) * 32) * UNIT, UNIT, bar_rx);
      }
      if (b < NFFN) {
#pragma unroll 1
        for (int u = 0; u < 12; u++) {
          const uint32_t dst = base + unit_of(u < 4 ? FT_G : (u < 8 ? FT_U : FT_D), u & 3);
          if (elect_one()) mbar_expect_tx(bar_box + u * 8, UNIT);
          if (u == FB0 || u == 2 || u == FB2) mbar_wait(bar_ring + (u == FB2 ? 16 : (u + 6) & 8), 0);
          if (u >= FPACE) mbar_wait(bar_box + (u - FPACE) * 8, 0);
          if (elect_one()) {
            if (u < 8) tma2d(dst, u < 4 ? &maps.wg : &maps.wu, b * 32, (u & 3) * 256, bar_box + u * 8);
            else tma3d(dst, &maps.wd, 0, b * 32, (u - 8) * 4, bar_box + u * 8);
          }
        }
      }
    } else if (warp == 9) {
      const uint32_t target = 8 * (epoch + 1);
      uint32_t hmask = 0;
#pragma unroll 1
      for (int i = 0; i < 16; i++) {
        if (i == HDX) mbar_wait(bar_mod, 0);
        const uint32_t need = i == 15 ? 0xffffu : 1u << ((2 * cj + i) & 15);
        if (i >= NRS && (hmask & need) != need) {
          uint32_t n = 0;
          do { hmask = __ballot_sync(0xffffffffu, ld_acquire(&g_cnt_h[rb * 32 + (lane & 15)]) == epoch + 1); watchdog(n); } while ((hmask & need) != need);
          PROF(1, lane == 0 && i == NRS, 26);
          fence_async();
        }
        mbar_wait(xempty + (i & 3) * 8, ((i >> 2) & 1) ^ 1);
        if (elect_one()) {
          mbar_expect_tx(xfull + (i & 3) * 8, UNIT);
          if (i < NRS) tma2d(base + (i & 3) * GST_BYTES, &maps.x, ((2 * cj + i) & 15) * 64, rb * 128, xfull + (i & 3) * 8);
          else bulk_load_stream(base + (i & 3) * GST_BYTES, g_act + (uint32_t)(rb * 80 + ((2 * cj + i) & 15)) * UNIT, UNIT, xfull + (i & 3) * 8);
        }
      }
      prefetch_map(&maps.wo);
#pragma unroll 1
      for (int t = 0; t < 4; t++) {
        if (t & 1) mbar_wait(bar_od, t >> 1);
#pragma unroll 1
        for (int p = 0; p < 32768 / OPS; p++) {
          const uint32_t w = p / (16384 / OPS), c = (p / (8192 / OPS)) & 1, off = w * 8192 + (p % (8192 / OPS)) * OPS;
          mbar_wait(bar_ofull + (t & 1) * 16 + w * 8, t >> 1);
          if (elect_one()) {
            bulk_store(g_act + (uint32_t)(rb * 80 + 16 + (cj * 4 + t) * 2 + c) * UNIT + off, base + unit_of(QT, 2 * t + c) + off, OPS);
            asm volatile("cp.async.bulk.commit_group;" ::: "memory");
            asm volatile("cp.async.bulk.wait_group.read %0;" ::"n"(OFL) : "memory");
          }
        }
        if (elect_one()) {
          asm volatile("cp.async.bulk.wait_group.read 0;" ::: "memory");
          mbar_arrive(t < 3 ? bar_ofree + t * 8 : bar_res);
          asm volatile("cp.async.bulk.wait_group 0;" ::: "memory");
          fence_async();
          red_release(&g_cnt_o[((rb * 4 + t) * 2 + (cj >> 2)) * 32], 2);
        }
        if (t) {
          wait_counter(&g_cnt_o[(rb * 8 + 2 * t + (cj & 1)) * 32], target);
          if (t & 1) wait_counter(&g_cnt_o[(rb * 8 + (t == 1 ? cj & 1 : 7 - (cj & 1))) * 32], target);
          if (elect_one()) mbar_arrive(t == 1 ? bar_ofree + 24 : bar_cnt + t * 8 - 16);
        }
      }
      PROF(2, lane == 0, 27);
      const uint32_t tag = epoch % 3 + 1;
      const uint32_t* inbox = g_cand + (lane & 15);
      mbar_wait(bar_ring + 16, 0);
      uint32_t c0 = ld_relaxed(inbox), n = 0;
#define CAND_STEP(cv)                                                                                        \
      {                                                                                                      \
        const bool valid = (cv & 3u) == tag, all = __all_sync(0xffffffffu, valid);                           \
        const uint32_t best = __reduce_max_sync(0xffffffffu, valid ? cv : 0u);                               \
        const uint32_t blk = __ffs(__ballot_sync(0xffffffffu, cv == best)) - 1;                              \
        if (best) sts2(par + PAR_CONST + 56, best, (blk << 7 | (~best >> 2 & 127)) | (all ? 0x1800 : 0x800)); \
        if (all) break;                                                                                      \
        cv = ld_relaxed(inbox);                                                                              \
      }
      while (true) { CAND_STEP(c0) watchdog(n); }
    } else {
      const int t2 = tid - 320;
      mbar_wait(bar_hpub + (warp & 1) * 8, 0);
      PROF(1, t2 == 0, 24);
#pragma unroll 1
      for (int c = 0; c < 8; c++) {
        const uint32_t off = (warp & 1) * UNIT + c * 2048 + lane * 16;
        uint8_t* dst = g_act + (uint32_t)(rb * 80 + cj * 2) * UNIT + off;
        const uint4 v0 = lds4(stage + off), v1 = lds4(stage + off + 512), v2 = lds4(stage + off + 1024), v3 = lds4(stage + off + 1536);
        stg4(dst, v0); stg4(dst + 512, v1); stg4(dst + 1024, v2); stg4(dst + 1536, v3);
      }
      __syncwarp();
      PROF(1, t2 == 0, 15);
      if (lane == 0) {
        mbar_arrive(bar_pread);
        red_release(&g_cnt_h[rb * 32 + cj * 2 + (warp & 1)], 1);
        PROF(1, t2 == 0, 25);
        prefetch_map(&maps.wg); prefetch_map(&maps.wu); prefetch_map(&maps.wd); prefetch_map(&maps.out);
      }
      __syncwarp();
      if (b < NFFN) {
        mbar_wait(bar_go2, 0);
        const __nv_bfloat16* pg = ((b & 1) ? P.w_up : P.w_gate) + (b >> 1) * 64 + (size_t)t2 * FF;
        const __nv_bfloat16* pd = P.w_down + (size_t)b * 32768 + t2 * 64;
        PROF(2, t2 == 0, 13);
#pragma unroll 1
        for (int i = 0; i < WN; i += WB) {
          uint32_t v[WB];
#pragma unroll
          for (int u = 0; u < WB; u++) {
            const int k = i + u;
            asm volatile("ld.global.cg.L2::128B.u32 %0, [%1];" : "=r"(v[u]) : "l"(k < 16 ? pg + (size_t)k * 64 * FF : pd + (k - 16) * 4096));
          }
#pragma unroll
          for (int u = 1; u < WB; u++) v[0] ^= v[u];
          sts1(par + PAR_SINK + t2 * 4, v[0]);
        }
        PROF(2, t2 == 0, 14);
      }
      const uint32_t tag = epoch % 3 + 1;
      mbar_wait(bar_go, 0);
      if (warp == 10) {
        const uint32_t* src = g_mod + 2 * DM + cj * 128 + lane * 4;
        const uint2 wr = *reinterpret_cast<const uint2*>(P.w_r + cj * 128 + lane * 4);
        uint4 vga, vsb, vcb, vgb;
        uint32_t n = 0;
        do {
          vga = ld_relaxed4(src); vsb = ld_relaxed4(src + DM); vcb = ld_relaxed4(src + 2 * DM); vgb = ld_relaxed4(src + 3 * DM);
          watchdog(n);
        } while (!__all_sync(0xffffffffu, tag_ok(vga, tag) && tag_ok(vsb, tag) && tag_ok(vcb, tag) && tag_ok(vgb, tag)));
        const float c0 = rbf(1.f + bf_hi(vcb.x)), c1 = rbf(1.f + bf_hi(vcb.y)), c2 = rbf(1.f + bf_hi(vcb.z)), c3 = rbf(1.f + bf_hi(vcb.w));
        const float a0 = c0 * bf_lo(wr.x), a1 = c1 * bf_hi(wr.x), a2 = c2 * bf_lo(wr.y), a3 = c3 * bf_hi(wr.y);
        const uint32_t h0 = pack_bf(a0, a1), h1 = pack_bf(a2, a3);
        const uint32_t t1 = par + PAR_T1 + (lane >> 2) * 64 + (lane & 1) * 32 + (lane & 2) * 2;
        sts1(t1, h0); sts1(t1 + 8, pack_bf(a0 - bf_lo(h0), a1 - bf_hi(h0)));
        sts1(t1 + 16, h1); sts1(t1 + 24, pack_bf(a2 - bf_lo(h1), a3 - bf_hi(h1)));
        sts4(par + PAR_T2 + lane * 32, make_uint4(pack_bf(c0, c1), __byte_perm(vsb.x, vsb.y, 0x7632), __byte_perm(vgb.x, vgb.y, 0x7632), __byte_perm(vga.x, vga.y, 0x7632)));
        sts4(par + PAR_T2 + lane * 32 + 16, make_uint4(pack_bf(c2, c3), __byte_perm(vsb.z, vsb.w, 0x7632), __byte_perm(vgb.z, vgb.w, 0x7632), __byte_perm(vga.z, vga.w, 0x7632)));
      } else {
        const uint4 g = poll4((lane & 2) ? g_mod + 8 - (lane & 1) * 4 : g_mod + 5 * DM + b * 8 + (lane & 1) * 4, tag);
        sts1(par + PAR_CONST + 60, 0);
        if (lane < 2) sts4(par + PAR_CONST + 16 + lane * 16, g);
        else if (lane < 4) sts2(par + PAR_CONST + (lane - 2) * 8, __float_as_uint(untag_sum(g.x, g.y) + untag_sum(g.z, g.w)), epoch);
      }
      __syncwarp();
#pragma unroll 4
      for (int q = XR; q < XE; q++) st_b128(g_xch + ((size_t)b * 8 * 256 + q * 64 + t2) * 4, (epoch & 1) << 16, 0, 0, 0);
      for (int q = 0; q < 2; q++) st_relaxed4(g_stats + ((size_t)cj * SEQ + rb * 128 + q * 64 + t2) * 4, 0, 0, 0, 0);
      if (b < NFFN)
        for (int q = 0; q < 4; q++) st_relaxed4(g_ypart + ((size_t)(q * 32 + (t2 >> 1)) * NFFN + b) * 8 + (t2 & 1) * 4, 0, 0, 0, 0);
      st_relaxed4(g_row + rb * 2 * DM + (t2 >> 5) * DM + cj * 128 + (t2 & 31) * 4, 0, 0, 0, 0);
      __threadfence();
      mbar_arrive(bar_par);
      mbar_wait(bar_gate, 0);
      uint32_t have = 0, n = 0;
      while (true) {
        const uint32_t st = lds1(par + PAR_CONST + 60) >> 7;
        if ((st & 31) != have) {
          const uint32_t* hsrc = g_row + (st & 15) * 2 * DM + t2 * 4;
          uint4 hv[4];
          bool ok = true;
#pragma unroll
          for (int i = 0; i < 4; i++) hv[i] = ld_pairs(hsrc + i * 256);
#pragma unroll
          for (int i = 0; i < 4; i++) {
            sts2(base + ((FT_G >> i * 4) & 15) * UNIT + (warp & 1) * 8192 + 256 + lane * 8, hv[i].x, hv[i].z);
            ok = ok && hv[i].y == tag && hv[i].w == tag;
          }
          have = __all_sync(0xffffffffu, ok) ? st & 31 : 0;
        }
        if ((st ^ have) == 32) break;
        watchdog(n);
      }
      mbar_arrive(bar_sel);
    }
    __syncwarp();
    cluster_arrive();
    {
      const uint32_t tag = epoch % 3 + 1, t3 = tid - 256;
      mbar_wait(bar_win, 0);
      uint2 win = lds2(par + PAR_CONST + 56);
      win.y &= 0x7ff;
      const uint32_t* fsrc = g_row + (win.y >> 7) * 2 * DM + (b >> 1) * 16 + (t3 & 3) * 4 + (b & 1) * 2;
      const uint32_t* ysrc = g_ypart + (size_t)b * NFFN * 8 + min(t3, NFFN - 1) * 4;
      uint2 fh = ld_pair(fsrc), fx = ld_pair(fsrc + DM);
      if (PSL) __nanosleep(PSL);
      uint4 ya = ld_relaxed4(ysrc), yb = ld_relaxed4(ysrc + NFFN * 4);
      const float rwin = __uint_as_float(((int)win.x < 0 ? win.x & 0x7fffffffu : ~win.x) & ~0x1ffu);
      const float rs = rbf(rcp(1.f + __expf(-rbf(rwin))));
      uint32_t n = 0;
      while (__any_sync(0xffffffffu, fh.y != tag || fx.y != tag)) { fh = ld_pair(fsrc); fx = ld_pair(fsrc + DM); watchdog(n); }
      while (!__all_sync(0xffffffffu, tag_ok(ya, tag) && tag_ok(yb, tag))) {
        if (!tag_ok(ya, tag)) ya = ld_relaxed4(ysrc);
        if (!tag_ok(yb, tag)) yb = ld_relaxed4(ysrc + NFFN * 4);
        watchdog(n);
      }
      __syncwarp();
      PROF(8, t3 == 0, 5);
      float y0 = untag_sum(ya.x, yb.x), y1 = untag_sum(ya.y, yb.y), y2 = untag_sum(ya.z, yb.z), y3 = untag_sum(ya.w, yb.w);
      const bool u1 = lane & 2, u2 = lane & 4;
      y0 = (u1 ? y2 : y0) + __shfl_xor_sync(0xffffffffu, u1 ? y0 : y2, 2);
      y1 = (u1 ? y3 : y1) + __shfl_xor_sync(0xffffffffu, u1 ? y1 : y3, 2);
      y0 = (u2 ? y1 : y0) + __shfl_xor_sync(0xffffffffu, u2 ? y0 : y1, 4);
      y0 += __shfl_xor_sync(0xffffffffu, y0, 8);
      if (!(lane & 8)) sts1(par + PAR_RED + 64 + (t3 >> 4) * 32 + ((lane & 1) * 4 + (lane & 2) + ((lane >> 2) & 1)) * 4, __float_as_uint(y0));
      bar_sync(4, 128);
      if (t3 < 4) {
        y0 = 0.f; y1 = 0.f;
#pragma unroll
        for (int w4 = 0; w4 < 7; w4++) {
          const uint2 v = lds2(par + PAR_RED + 64 + w4 * 32 + t3 * 8);
          y0 += __uint_as_float(v.x); y1 += __uint_as_float(v.y);
        }
        const uint2 gv = lds2(par + PAR_CONST + 16 + t3 * 8);
        const uint32_t upd = hmul2(pack_bf(y0, y1), pack_bf(rs, rs));
        *reinterpret_cast<uint32_t*>(P.out + (size_t)win.y * DM + b * 8 + t3 * 2) =
            hadd2(fx.x, hmul2(__byte_perm(gv.x, gv.y, 0x7632), hadd2(fh.x, upd)));
        if (b == 0 && t3 == 0) st_relaxed(&g_epoch, epoch + 1);
      }
      PROF(31, t3 == 0, 36);
    }
    cluster_wait();
  } else {
    const int wg = warp >> 2;

    uint32_t tag;
    {
      uint32_t* const pmod = g_modp + rank * 2 * DM + (b >> 1) * 32 + lane;
      uint32_t* const pln = g_ln1 + (rb * 128 + cj * 16 + warp) * 4;
      const uint32_t cv = ldg_nc1(P.c + rank * 512 + tid * 2);
      const uint32_t epoch = ld_relaxed(&g_epoch);
      if (warp == 0) st_relaxed(pmod, 0);
      if (lane == 0) { st_b128(pln, 0, 0, 0, 0); st_b128(pln + 32, 0, 0, 0, 0); }
      asm volatile("setmaxnreg.inc.sync.aligned.u32 232;");
      sts1(par + tid * 4, pack_bf(silu_f(bf_lo(cv)), silu_f(bf_hi(cv))));
      bar_sync(1, 320);
      tag = epoch % 3 + 1;
#pragma unroll
      for (int part = 0; part < 3; part++) {
        if (part != 1) {
          const uint32_t xa = base + (2 + part / 2) * GST_BYTES + warp * 2048 + lane * 16;
          mbar_wait(bar_hx + part * 4, 0);
          float s0 = 0.f, s1 = 0.f, q0 = 0.f, q1 = 0.f;
#pragma unroll
          for (int q = 0; q < 4; q++) {
            const uint4 xv = lds4(xa + q * 512);
            const uint32_t u[4] = {xv.x, xv.y, xv.z, xv.w};
#pragma unroll
            for (int e = 0; e < 4; e++) { const float lo = bf_lo(u[e]), hi = bf_hi(u[e]); s0 += lo; s1 += hi; q0 += lo * lo; q1 += hi * hi; }
          }
          s0 += s1; q0 += q1;
#pragma unroll
          for (int o = 16; o > 0; o >>= 1) { s0 += __shfl_xor_sync(0xffffffffu, s0, o); q0 += __shfl_xor_sync(0xffffffffu, q0, o); }
          const float mean = s0 * (1.f / DM);
          float mb, sd;
          ln_scalars(mean, fmaxf(q0 * (1.f / DM) - mean * mean, 0.f), mb, sd);
          uint32_t ih, il;
          split_inv(sd, ih, il);
          if (lane == 0) st_b128(pln + part * 16, pack_bf(mb, mb), ih, il, tag);
          PROF(1, tid == 0 && part == 2, 4);
        } else {
          float acc[8];
#pragma unroll
          for (int e = 0; e < 8; e++) acc[e] = 0.f;
          const uint32_t wa = stage + (tid >> 2) * 64 + (((tid ^ (tid >> 3)) & 3) << 4), sa = par + (tid >> 3) * 4, sh = (tid & 4) ? 0x3244 : 0x1044;
          mbar_wait(bar_hw, 0);
#pragma unroll
          for (int p = 0; p < 8; p++) {
            const uint4 w = lds4(wa + p * 4096);
            const float s = __uint_as_float(__byte_perm(lds1(sa + p * 128), 0, sh));
            acc[0] += s * bf_lo(w.x); acc[1] += s * bf_hi(w.x); acc[2] += s * bf_lo(w.y); acc[3] += s * bf_hi(w.y);
            acc[4] += s * bf_lo(w.z); acc[5] += s * bf_hi(w.z); acc[6] += s * bf_lo(w.w); acc[7] += s * bf_hi(w.w);
          }
#pragma unroll
          for (int e = 0; e < 4; e++) {
            const bool up = lane & 16;
            acc[e] = (up ? acc[e + 4] : acc[e]) + __shfl_xor_sync(0xffffffffu, up ? acc[e] : acc[e + 4], 16);
          }
#pragma unroll
          for (int e = 0; e < 2; e++) {
            const bool up = lane & 8;
            acc[e] = (up ? acc[e + 2] : acc[e]) + __shfl_xor_sync(0xffffffffu, up ? acc[e] : acc[e + 2], 8);
          }
          {
            const bool up = lane & 4;
            acc[0] = (up ? acc[1] : acc[0]) + __shfl_xor_sync(0xffffffffu, up ? acc[0] : acc[1], 4);
          }
          sts1(base + 2 * GST_BYTES + warp * 2048 + ((lane & 3) * 8 + (lane >> 2)) * 4, __float_as_uint(acc[0]));
          bar_sync(1, 256);
          if (warp == 0) {
            float s = 0.f;
#pragma unroll
            for (int w8 = 0; w8 < 8; w8++) s += __uint_as_float(lds1(base + 2 * GST_BYTES + w8 * 2048 + lane * 4));
            st_relaxed(pmod, (__float_as_uint(s) & ~3u) | tag);
          }
          PROF(1, tid == 0, 3);
        }
      }
      cluster_wait();
      if (wg == 1) bar_arrive(2, 256);
    }

    float f0 = 0.f, f1 = 0.f;
    const uint32_t rempty = lane < 2 ? mapa(bempty, lane & 1) : 0;
    constexpr uint32_t GE = NSLOT * 8 + 32;
    float o[64], s[64];
#pragma unroll 1
    for (int ps = 0; ps < 3; ps++) {
      {
        const uint32_t xt = ps == 1 ? XT1 : XT2, wt = ps == 1 ? WT1 : WT2;
        const int nst = ps == 2 ? 28 : 14;
        if (ps == 0) {
          float ga[64], gb[64];
#pragma unroll
          for (int i = 0; i < 64; i++) { ga[i] = 0.f; gb[i] = 0.f; }
          uint32_t a[2][16];
          const uint32_t l = fresh_lane();
          uint32_t fa[4];
#pragma unroll
          for (int kk = 0; kk < 4; kk++) fa[kk] = (base + wg * 8192 + frag_offset(warp)) ^ (kk * 32);
          const uint32_t mt = par + (l & 3) * 16;
          auto fetch = [&](int i, uint32_t (&f)[16], uint32_t z) {
            mbar_wait(xfull + (i & 3) * 8, i >> 2);
#pragma unroll
            for (int kk = 0; kk < 4; kk++) ldmatrix4(fa[kk] + (i & 3) * GST_BYTES + z, f[4 * kk], f[4 * kk + 1], f[4 * kk + 2], f[4 * kk + 3]);
          };
          uint4 r0, r1;
          {
            const uint32_t t7 = (warp & 3) * 32 + l;
            const uint32_t* pm = g_modp + wg * DM + ((cj * 128 + t7 * 4) & (DM - 1));
            const uint32_t* pr = g_ln1 + (rb * 128 + warp * 16 + (l >> 2)) * 4;
            uint4 m0 = ld_relaxed4(pm), m1 = ld_relaxed4(pm + 2 * DM);
            r0 = ld_b128(pr); r1 = ld_b128(pr + 32);
            fetch(0, a[0], 0); fetch(1, a[1], 0);
            uint32_t n = 0;
            bool written = false;
#pragma unroll 1
            while (true) {
              uint32_t miss;
              asm volatile("{ .reg .pred p0, p1, p2, p3; .reg .b32 t, u;\n"
                           "lop3.b32 t, %1, %2, %19, 0x7e; lop3.b32 u, %3, %4, %19, 0x7e; or.b32 t, t, u; and.b32 t, t, 3; setp.ne.u32 p0, t, 0;\n"
                           "lop3.b32 t, %5, %6, %19, 0x7e; lop3.b32 u, %7, %8, %19, 0x7e; or.b32 t, t, u; and.b32 t, t, 3; setp.ne.u32 p1, t, 0;\n"
                           "setp.ne.u32 p2, %12, %19; setp.ne.u32 p3, %16, %19;\n"
                           "@p0 ld.relaxed.gpu.global.v4.u32 {%1, %2, %3, %4}, [%17];\n"
                           "@p1 ld.relaxed.gpu.global.v4.u32 {%5, %6, %7, %8}, [%17 + 8192];\n"
                           "@p2 ld.relaxed.gpu.global.v4.u32 {%9, %10, %11, %12}, [%18];\n"
                           "@p3 ld.relaxed.gpu.global.v4.u32 {%13, %14, %15, %16}, [%18 + 128];\n"
                           "or.pred p0, p0, p1; or.pred p2, p2, p3; vote.sync.any.pred p0, p0, 0xffffffff; vote.sync.any.pred p2, p2, 0xffffffff;\n"
                           "selp.u32 t, 1, 0, p0; selp.u32 u, 2, 0, p2; or.b32 %0, t, u; }"
                           : "=r"(miss), "+r"(m0.x), "+r"(m0.y), "+r"(m0.z), "+r"(m0.w), "+r"(m1.x), "+r"(m1.y), "+r"(m1.z), "+r"(m1.w),
                             "+r"(r0.x), "+r"(r0.y), "+r"(r0.z), "+r"(r0.w), "+r"(r1.x), "+r"(r1.y), "+r"(r1.z), "+r"(r1.w)
                           : "l"(pm), "l"(pr), "r"(tag) : "memory");
              if (!(miss & 1) && !written) {
                written = true;
                float c0 = untag_sum(m0.x, m1.x), c1 = untag_sum(m0.y, m1.y), c2 = untag_sum(m0.z, m1.z), c3 = untag_sum(m0.w, m1.w);
                if (wg) { c0 = 1.f + rbf(c0); c1 = 1.f + rbf(c1); c2 = 1.f + rbf(c2); c3 = 1.f + rbf(c3); }
                const uint32_t d = par + (t7 >> 2) * 64 + (t7 & 1) * 32 + (t7 & 2) * 2 + (wg ? 0 : 8);
                sts1(d, pack_bf(c0, c1));
                sts1(d + 16, pack_bf(c2, c3));
                mbar_arrive(bar_mod);
              }
              if (!miss) break;
              watchdog(n);
            }
          }
          const uint32_t zero = r0.w ^ tag;
          auto normalize = [&](uint32_t (&f)[16]) {
#pragma unroll
            for (int k = 0; k < 16; k += 2) { f[k] = ln_norm(f[k], r0.x, r0.y, r0.z); f[k + 1] = ln_norm(f[k + 1], r1.x, r1.y, r1.z); }
          };
          auto modulate = [&](int i, uint32_t (&f)[16]) {
#pragma unroll
            for (int kk = 0; kk < 4; kk++) {
              const uint4 m = lds4(mt + i * 256 + kk * 64);
              f[4 * kk] = MODUL(f[4 * kk], m.x, m.z); f[4 * kk + 1] = MODUL(f[4 * kk + 1], m.x, m.z);
              f[4 * kk + 2] = MODUL(f[4 * kk + 2], m.y, m.w); f[4 * kk + 3] = MODUL(f[4 * kk + 3], m.y, m.w);
            }
            keep(f);
            mbar_arrive_pred(xempty + (i & 3) * 8, l == 0);
          };
          auto publish = [&](int u, uint32_t (&f)[16]) {
#pragma unroll
            for (int kk = 0; kk < 4; kk++) stmatrix4(fa[kk] + OFF_STAGE + u * UNIT, f[4 * kk], f[4 * kk + 1], f[4 * kk + 2], f[4 * kk + 3]);
            __syncwarp();
            mbar_arrive_pred(bar_hpub + u * 8, l == 0);
          };
          auto multiply = [&](int i, uint32_t (&f)[16]) {
            mbar_wait(gfull + (i & 3) * 8, i >> 2);
            const uint64_t db = make_desc(base + (i & 3) * GST_BYTES + UNIT, 8192, 1024);
            wg_fence();
#pragma unroll
            for (int kk = 0; kk < 4; kk++) mma256_rs(ga, gb, f[4 * kk], f[4 * kk + 1], f[4 * kk + 2], f[4 * kk + 3], db + kk * 128);
            wg_commit();
          };
          auto next = [&](int i, uint32_t (&f)[16]) {
            wg_wait<1>();
            mbar_arrive_cl(rempty, GE + ((i + 2) & 3) * 8);
            uint32_t z = zero;
#pragma unroll
            for (int k = 0; k < 16; k += 2) asm volatile("lop3.b32 %0, %1, %2, %0, 0xA8;" : "+r"(z) : "r"(f[k]), "r"(f[k + 1]));
            fetch(i, f, z);
            normalize(f); modulate(i, f); multiply(i, f);
          };
          normalize(a[0]); normalize(a[1]);
          keep(a[0]); keep(a[1]);
          mbar_wait(bar_mod, 0);
          PROF(1, tid == 0, 2);
          modulate(0, a[0]); multiply(0, a[0]); publish(0, a[0]);
          modulate(1, a[1]); multiply(1, a[1]); publish(1, a[1]);
#pragma unroll 1
          for (int i = 2; i < NRS; i += 2) { next(i, a[0]); next(i + 1, a[1]); }
          wg_wait<1>();
          mbar_arrive_cl(rempty, GE + ((NRS + 2) & 3) * 8);
#pragma unroll 1
          for (int i = NRS; i < 14; i++) {
            mbar_wait(xfull + (i & 3) * 8, (i >> 2) & 1);
            mbar_wait(gfull + (i & 3) * 8, (i >> 2) & 1);
            const uint32_t xa = base + (i & 3) * GST_BYTES;
            const uint64_t da = make_desc(xa + wg * 8192, 16, 1024), db = make_desc(xa + UNIT, 8192, 1024);
            if (i == 13) bar_sync(2 + wg, 256);
            wg_fence();
#pragma unroll
            for (int kk = 0; kk < 4; kk++) mma256_ss(ga, gb, da + kk * 2, db + kk * 128, 1);
            wg_commit();
            if (i == 13) bar_arrive(3 - wg, 256);
            wg_wait<1>();
            uint32_t z = zero;
#pragma unroll
            for (int k = 0; k < 16; k += 2) asm volatile("lop3.b32 %0, %1, %2, %0, 0xA8;" : "+r"(z) : "r"(a[1][k]), "r"(a[1][k + 1]));
            mbar_arrive_cl(rempty, GE + ((i + 3) & 3) * 8 + z);
            mbar_arrive_pred(xempty + ((i + 3) & 3) * 8, l == 0 && i != NRS);
          }
          mbar_wait(xfull + 16, 1);
          wg_wait<0>();
          keep(ga); keep(gb);
#pragma unroll
          for (int i = 0; i < 64; i++) {
            asm volatile("mov.b32 %0, %1;" : "=f"(s[i]) : "f"(ga[i]));
            asm volatile("mov.b32 %0, %1;" : "=f"(o[i]) : "f"(gb[i]));
          }
        } else {
          float ga[64], gb[64];
#pragma unroll
          for (int i = 0; i < 64; i++) {
            asm volatile("mov.b32 %0, %1;" : "=f"(ga[i]) : "f"(s[i]));
            asm volatile("mov.b32 %0, %1;" : "=f"(gb[i]) : "f"(o[i]));
          }
#pragma unroll 1
          for (int i = 0; i < nst; i++) {
            mbar_wait(gfull + (i & 3) * 8, (i >> 2) & 1);
            const uint64_t da = make_desc(base + unit_of(xt, i & 3) + wg * 8192, 16, 1024), db = make_desc(base + unit_of(wt, i & 3), 8192, 1024);
            if (i == nst - 1) bar_sync(2 + wg, 256);
            wg_fence();
#pragma unroll
            for (int kk = 0; kk < 4; kk++) mma256_ss(ga, gb, da + kk * 2, db + kk * 128, kk ? 1 : i);
            wg_commit();
            if (i == nst - 1) bar_arrive(3 - wg, 256);
            wg_wait<1>();
            mbar_arrive_cl(rempty, GE + ((i + 3) & 3) * 8, i != 0);
            PROF(4, tid == 0 && (i & 3) == 0, 40 + (ps - 1) * 4 + i / 4);
          }
          wg_wait<0>();
          keep(ga); keep(gb);
#pragma unroll
          for (int i = 0; i < 64; i++) {
            asm volatile("mov.b32 %0, %1;" : "=f"(s[i]) : "f"(ga[i]));
            asm volatile("mov.b32 %0, %1;" : "=f"(o[i]) : "f"(gb[i]));
          }
        }
        mbar_arrive_cl(rempty, GE + (ps == 2 ? 24 : 8));
        if (ps == 2) break;
      }
      const uint32_t qw = base + wg * 8192, qt = QT >> (16 * ps), at = ps ? AT1 : AT0;
      {
        const uint32_t wt = ps ? WT1 : WT0;
        const uint64_t da0 = make_desc(qw + unit_of(qt, 2), 16, 1024), da1 = make_desc(qw + unit_of(qt, 3), 16, 1024);
        const uint64_t db0 = make_desc(base + unit_of(wt, 2), 8192, 1024), db1 = make_desc(base + unit_of(wt, 3), 8192, 1024);
        mbar_wait(gfull + 16, 1);
        bar_sync(2 + wg, 256);
        wg_fence();
#pragma unroll
        for (int kk = 0; kk < 4; kk++) mma_ss<1>(s, da0 + kk * 2, db0 + kk * 128, 1);
        wg_commit();
        mbar_wait(xfull + 24, 1);
        mbar_wait(gfull + 24, 1);
        wg_fence();
#pragma unroll
        for (int kk = 0; kk < 4; kk++) mma_ss<1>(s, da1 + kk * 2, db1 + kk * 128, 1);
        wg_commit();
        bar_arrive(3 - wg, 256);
        mbar_wait(ps == 0 ? bar_pread : bar_ofree + 8, 0);
        wg_wait<0>();
        keep(s);
        PROF(2, tid == 0, 8 + ps * 8);
        store_chunk<0>(s, qw + unit_of(qt, 0) + frag_offset(warp));
        store_chunk<1>(s, qw + unit_of(qt, 1) + frag_offset(warp));
        fence_async_smem();
        bar_sync(2 + wg, 256);
        wg_fence();
#pragma unroll
        for (int kk = 0; kk < 8; kk++) mma_ss<1>(o, (kk < 4 ? da0 : da1) + (kk & 3) * 2, (kk < 4 ? db0 : db1) + UNIT / 16 + (kk & 3) * 128, 1);
        wg_commit();
        mbar_wait(bfull, 0);
        wg_fence();
        issue_qk(s, qw + unit_of(qt, 0), qw + unit_of(qt, 1), base + unit_of(at, 0));
        wg_commit();
        bar_arrive(3 - wg, 256);
        wg_wait<1>();
        keep(o);
        mbar_arrive_cl(rempty, GE + 16);
        mbar_arrive_cl(rempty, GE + 24);
        store_chunk<0>(o, qw + unit_of(qt, 2) + frag_offset(warp));
        store_chunk<1>(o, qw + unit_of(qt, 3) + frag_offset(warp));
        wg_wait<0>();
        keep(s);
        mbar_arrive_cl(rempty, 0);
      }
      PROF(4, tid == 0 && ps == 1, 61);
      float l0 = 0.f, l1 = 0.f;
      auto step = [&](auto odd_c, const int j, uint32_t (&pw)[32], uint32_t (&pr)[32]) {
        constexpr bool ODD = decltype(odd_c)::value;
        const bool first = !ODD && (j & 2) == 0, last = ODD && j == 7;
        const uint32_t ph = (j >> 1) & 1;
        float i0, i1, a0, a1;
        const bool so = !ODD && j == 4;
        if (so) { i0 = inv_quad_sum(l0); i1 = inv_quad_sum(l1); l0 = 0.f; l1 = 0.f; }
        bool redo = !ODD && (j | ps) == 0;
        while (true) {
          if (redo) {
            float m0 = fmaxf(s[0], s[1]), m1 = fmaxf(s[2], s[3]);
#pragma unroll
            for (int i = 1; i < 16; i++) { m0 = fmaxf(m0, fmaxf(s[4 * i], s[4 * i + 1])); m1 = fmaxf(m1, fmaxf(s[4 * i + 2], s[4 * i + 3])); }
            m0 = fmaxf(m0, __shfl_xor_sync(0xffffffffu, m0, 1)); m1 = fmaxf(m1, __shfl_xor_sync(0xffffffffu, m1, 1));
            m0 = fmaxf(m0, __shfl_xor_sync(0xffffffffu, m0, 2)); m1 = fmaxf(m1, __shfl_xor_sync(0xffffffffu, m1, 2));
            m0 *= SCL2; m1 *= SCL2;
            if (!first) {
              m0 = fmaxf(m0, f0); m1 = fmaxf(m1, f1);
              const float c0 = ex2(f0 - m0), c1 = ex2(f1 - m1);
              l0 *= c0; l1 *= c1;
              wg_wait<0>();
              keep(o);
#pragma unroll
              for (int i = 0; i < 16; i++) { o[4 * i] *= c0; o[4 * i + 1] *= c0; o[4 * i + 2] *= c1; o[4 * i + 3] *= c1; }
            }
            f0 = m0; f1 = m1;
          }
          float b0 = 0.f, b1 = 0.f;
          a0 = 0.f; a1 = 0.f;
#pragma unroll
          for (int i = 0; i < 16; i++) {
            const float e0 = ex2(fmaf(s[4 * i], SCL2, -f0)), e1 = ex2(fmaf(s[4 * i + 1], SCL2, -f0));
            const float e2 = ex2(fmaf(s[4 * i + 2], SCL2, -f1)), e3 = ex2(fmaf(s[4 * i + 3], SCL2, -f1));
            a0 += e0; b0 += e1; a1 += e2; b1 += e3;
            pw[2 * i] = pack_bf(e0, e1); pw[2 * i + 1] = pack_bf(e2, e3);
            if (i == VREL) {
#pragma unroll
              for (int k = 0; k < 2 * VREL + 2; k++) asm volatile("" : "+r"(pw[k])::"memory");
              mbar_wait(bar_mod, 0);
              wg_wait<0>();
              mbar_arrive_cl(rempty, ODD ? 16 : 0, !redo && (ODD || j));
#pragma unroll
              for (int k = 4 * VREL + 4; k < 64; k++) asm volatile("" : "+f"(s[k])::"memory");
            }
          }
          a0 += b0; a1 += b1;
          if (redo) break;
          redo = __any_sync(0xffffffffu, !(a0 + a1 < 0x1p70f));
          if (first) {
            uint32_t m0 = __ballot_sync(0xffffffffu, a0 > 0x1p-50f), m1 = __ballot_sync(0xffffffffu, a1 > 0x1p-50f);
            m0 |= m0 >> 1; m1 |= m1 >> 1; m0 |= m0 >> 2; m1 |= m1 >> 2;
            redo = redo || (m0 & m1 & 0x11111111u) != 0x11111111u;
          }
          if (!redo) break;
        }
        l0 += a0; l1 += a1;
        keep(pw);
        keep(o);
        if (so) store_chunk<0>(o, i0, i1, qw + unit_of(qt, 0) + frag_offset(warp));
        keep(o);
        if (ODD && !(j & 2)) { fence_async_smem(); mbar_arrive_pred(bar_ofull + wg * 8, j > 4); }
        mbar_wait(bfull + (ODD ? 24 : 8), ph);
        bar_sync(2 + wg, 256);
        if (!last) {
          const uint32_t qn = qt >> (j >= 3 ? 8 : 0);
          wg_fence();
          issue_qk(s, qw + unit_of(qn, 0), qw + unit_of(qn, 1), base + unit_of(at, ODD ? 3 : 1));
          wg_commit();
          mbar_wait(bfull + (ODD ? 0 : 16), ODD ? ph ^ 1 : ph);
        }
        if (so) { store_chunk<1>(o, i0, i1, qw + unit_of(qt, 1) + frag_offset(warp)); keep(o); }
        wg_fence();
        issue_pv(o, pw, base + unit_of(at, ODD ? (last ? 3 : 0) : 2), !first);
        wg_commit();
        bar_arrive(3 - wg, 256);
        wg_wait<1>();
        keep(s);
        mbar_arrive_cl(rempty, ODD ? 24 : 8, !last);
        PROF(4, tid == 0 && ps == 1, 51 + j);
      };
      uint32_t pa[32], pb[32];
#pragma unroll 1
      for (int j = 0; j < 8; j += 2) {
        step(std::false_type{}, j, pa, pb);
        step(std::true_type{}, j + 1, pb, pa);
      }
      {
        const float i0 = inv_quad_sum(l0), i1 = inv_quad_sum(l1);
        wg_wait<0>();
        keep(o);
        mbar_arrive_cl(rempty, 24);
        store_chunk<0>(o, i0, i1, qw + unit_of(qt, 2) + frag_offset(warp));
        store_chunk<1>(o, i0, i1, qw + unit_of(qt, 3) + frag_offset(warp));
        fence_async_smem();
        mbar_arrive(bar_ofull + 16 + wg * 8);
      }
      PROF(2, tid == 0, 10 + ps * 8);
    }

    const int ln = fresh_lane(), g = ln >> 2, tq = ln & 3, ct = warp * 32 + ln;
    const bool lane0 = ln == 0;
    const int lrow0 = warp * 16 + g;
    const int grow0 = rb * 128 + lrow0;
    const uint32_t res = base + OFF_RES, trow = res + wg * 8192 + frag_offset(warp);
    uint32_t xr[32];
    uint4 sv[4], own;
    uint32_t* sp[4];
#pragma unroll
    for (int k = 0; k < 4; k++) sp[k] = g_stats + ((((tq >> 1) * 4 + k) ^ cj) * SEQ + grow0 + (tq & 1) * 8) * 4;
    {
      const uint64_t da = make_desc(base + wg * 8192, 16, 1024), db = make_desc(base, 8192, 1024);
      constexpr int U = UNIT / 16;
#define HALF_STAGE(acc, xu, wu) _Pragma("unroll") for (int kk = 0; kk < 4; kk++) mma_ss<1>(acc, da + (xu) * U + kk * 2, db + (wu) * U + kk * 128, 1)
      PROF(10, ct == PT, 19); STAMP(0);
      cluster_arrive();
      mbar_wait(gfull, 1);
      mbar_wait(gfull + 8, 1);
      bar_sync(2 + wg, 256);
      wg_fence();
      HALF_STAGE(o, 7, 1);
      HALF_STAGE(o, 8, 3);
      wg_commit();
      STAMP(16);
      mbar_wait(gfull + 16, 1);
      STAMP(17);
      wg_fence();
      HALF_STAGE(o, 6, 11);
      wg_commit();
      bar_arrive(3 - wg, 256);
      mbar_wait(bar_par, 0);
      uint32_t* xo = g_xch + ((size_t)b * 8 * 256 + ct) * 4;
      const uint32_t* xi = g_xch + ((size_t)(b ^ 2) * 8 * 256 + ct) * 4;
      const uint32_t par1 = (~lds1(par + PAR_CONST + 4) & 1) << 16;
      uint32_t ga[16];
      uint4 bw[8];
#define LOAD_PAR _Pragma("unroll") for (int i = 0; i < 8; i++) {                                                               \
        ga[2 * i] = lds1(par + PAR_T2 + i * 128 + tq * 16 + 12); ga[2 * i + 1] = lds1(par + PAR_T2 + i * 128 + 64 + tq * 16 + 12); \
        bw[i] = lds4(par + PAR_T1 + i * 64 + tq * 16);                                                                          \
        if (!(g & 1)) { bw[i].x = 0x3f803f80u; bw[i].y = 0x3f803f80u; }                                                         \
      }
      if (PPOS == 0) LOAD_PAR
      wg_wait<1>();
      mbar_arrive_pred(bar_rel, lane0);
      wg_wait<0>();
      keep(o);
      mbar_arrive_pred(bar_ring, lane0);
      PROF(8, ct == PT, 20); STAMP(1);
#define SEND(i) st_b128(xo + (i) * 1024, (pack_bf(o[8 * (i)], o[8 * (i) + 1]) & ~0x10000u) | par1, pack_bf(o[8 * (i) + 2], o[8 * (i) + 3]), \
                        pack_bf(o[8 * (i) + 4], o[8 * (i) + 5]), pack_bf(o[8 * (i) + 6], o[8 * (i) + 7]))
#pragma unroll
      for (int i = 0; i < NS1; i++) SEND(i);
      PROF(8, ct == PT, 21); STAMP(2);
      bar_sync(2 + wg, 256);
      wg_fence();
      HALF_STAGE(s, 7, 0);
      HALF_STAGE(s, 8, 2);
      HALF_STAGE(s, 6, 10);
      wg_commit();
      bar_arrive(3 - wg, 256);
      STAMP(18);
      mbar_wait(gfull + 24, 1);
#pragma unroll
      for (int i = NS1; i < 8; i++) SEND(i);
      uint4 v[8];
#pragma unroll
      for (int i = 0; i < 4; i++) v[i] = ld_b128(xi + i * 1024);
      if (PPOS == 1) LOAD_PAR
      STAMP(19);
      mbar_wait(bar_xres, 0);
      wg_wait<0>();
      mbar_arrive_pred(bar_ring + 8, lane0);
      bar_sync(2 + wg, 256);
      STAMP(20);
#pragma unroll
      for (int i = 4; i < 8; i++) v[i] = ld_b128(xi + i * 1024);
      mbar_wait(bar_xres, 0);
      wg_fence();
      HALF_STAGE(s, 9, 4);
      wg_commit();
      mbar_wait(bar_rx, 0);
      wg_fence();
      HALF_STAGE(s, 1, 5);
      wg_commit();
      bar_arrive(3 - wg, 256);
      STAMP(21);
      wg_wait<0>();
      keep(s);
      mbar_arrive_pred(bar_ring + 16, lane0);
      PROF(10, ct == PT, 23); STAMP(4);
#pragma unroll
      for (int i = 0; i < 16; i += 2) ldmatrix4((trow ^ ((i & 7) << 4)) + (i >> 3) * 16384, xr[2 * i], xr[2 * i + 1], xr[2 * i + 2], xr[2 * i + 3]);
      if (PPOS == 2) LOAD_PAR
      uint32_t pk[32];
      pack_p(s, pk);
      keep(pk);
      {
        uint32_t n = 0, miss;
        do {
          miss = 0;
#pragma unroll
          for (int i = 0; i < 8; i++) miss |= v[i].x ^ par1;
          miss = __any_sync(0xffffffffu, miss & 0x10000u);
          if (miss) {
#pragma unroll
            for (int i = 0; i < 8; i++)
              asm volatile("{ .reg .pred p; .reg .b32 t; xor.b32 t, %0, %5; and.b32 t, t, 0x10000; setp.ne.u32 p, t, 0;\n"
                           "@p ld.relaxed.gpu.global.v4.u32 {%0, %1, %2, %3}, [%4]; }"
                           : "+r"(v[i].x), "+r"(v[i].y), "+r"(v[i].z), "+r"(v[i].w) : "l"(xi + i * 1024), "r"(par1) : "memory");
          }
          watchdog(n);
        } while (miss);
      }
      PROF(8, ct == PT, 22); STAMP(3);
#pragma unroll
      for (int k = 0; k < 4; k++) sv[k] = ESV ? ld_b128(sp[k]) : make_uint4(0, 0, 0, 0);
      float ds[4] = {0.f, 0.f, 0.f, 0.f}, dl[4] = {0.f, 0.f, 0.f, 0.f}, q0[4] = {0.f, 0.f, 0.f, 0.f}, q1[4] = {0.f, 0.f, 0.f, 0.f};
#pragma unroll
      for (int i = 0; i < 8; i++) {
        const uint32_t u0 = hfma2(ga[2 * i], hadd2(pk[4 * i], v[i].x & ~0x10000u), xr[4 * i]);
        const uint32_t u1 = hfma2(ga[2 * i], hadd2(pk[4 * i + 1], v[i].y), xr[4 * i + 1]);
        const uint32_t u2 = hfma2(ga[2 * i + 1], hadd2(pk[4 * i + 2], v[i].z), xr[4 * i + 2]);
        const uint32_t u3 = hfma2(ga[2 * i + 1], hadd2(pk[4 * i + 3], v[i].w), xr[4 * i + 3]);
        xr[4 * i] = u0; xr[4 * i + 1] = u1; xr[4 * i + 2] = u2; xr[4 * i + 3] = u3;
        mma16816(ds, u0, u1, u2, u3, bw[i].x, bw[i].y);
        mma16816(dl, u0, u1, u2, u3, bw[i].z, bw[i].w);
        mma16816(q0, u0, u1, u2, u3, u0, u2);
        mma16816(q1, u0, u1, u2, u3, u1, u3);
      }
      const float sqa = __shfl_sync(0xffffffffu, (g & 1) ? q0[1] : q0[0], g * 4 + (g >> 1));
      const float sqb = __shfl_sync(0xffffffffu, (g & 1) ? q1[3] : q1[2], g * 4 + (g >> 1));
      own = (tq & 1) ? make_uint4(__float_as_uint(ds[2]), __float_as_uint(sqb), __float_as_uint(ds[3] + dl[3]), tag)
                                 : make_uint4(__float_as_uint(ds[0]), __float_as_uint(sqa), __float_as_uint(ds[1] + dl[1]), tag);
      if (tq < 2) st_b128(sp[0], own.x, own.y, own.z, own.w);
    }
    PROF(8, ct == PT, 29); STAMP(5);
    uint32_t mm, ih, il;
    float rbest;
    uint32_t wf[128];
    const uint32_t frow = (ln & 7) + (ln >> 4) * 8;
    const uint32_t wfo = base + (warp & 1) * 8192 + frow * 64 + ((((ln >> 3) & 1) ^ ((frow >> 1) & 3)) << 4);
#define LOAD_WF(m) _Pragma("unroll") for (int f = 0; f < 16; f++) {                                                   \
      const int r = ((f >> 1) * 4 + (m) * 2 + (f & 1)) * 4;                                                           \
      ldmatrix4t(((wfo + unit_of((m) ? FT_U : FT_G, warp >> 1)) ^ ((f & 1) * 32)) + (f >> 1) * 1024, wf[r], wf[r + 1], wf[r + 2], wf[r + 3]); \
    }
    bool early, wait1;
    {
#pragma unroll
      for (int i = 0; i < 16; i += 2) stmatrix4((trow ^ ((i & 7) << 4)) + (i >> 3) * 16384, xr[2 * i], xr[2 * i + 1], xr[2 * i + 2], xr[2 * i + 3]);
      const uint4 cst = lds4(par + PAR_CONST);
      const float A1 = __uint_as_float(cst.x), A2 = __uint_as_float(cst.z);
      uint32_t n = 0;
      early = false; wait1 = false;
#pragma unroll 1
      while (true) {
        uint32_t miss;
        asm volatile("{ .reg .pred p0, p1, p2, p3; .reg .b64 u, v; .reg .b128 w;\n"
                     "setp.ge.u32 p0, %22, 2; setp.ne.and.u32 p0, %4, %21, p0; setp.ne.u32 p1, %8, %21; setp.ne.u32 p2, %12, %21; setp.ne.u32 p3, %16, %21;\n"
                     "@p0 ld.relaxed.gpu.global.v4.u32 {%1, %2, %3, %4}, [%17];\n"
                     "@p1 ld.relaxed.gpu.global.v4.u32 {%5, %6, %7, %8}, [%18];\n"
                     "@p2 ld.relaxed.gpu.global.v4.u32 {%9, %10, %11, %12}, [%19];\n"
                     "@p3 ld.relaxed.gpu.global.v4.u32 {%13, %14, %15, %16}, [%20];\n"
                     "or.pred p0, p0, p1; or.pred p2, p2, p3; or.pred p0, p0, p2; vote.sync.any.pred p0, p0, 0xffffffff; selp.u32 %0, 1, 0, p0; }"
                     : "=r"(miss), "+r"(sv[0].x), "+r"(sv[0].y), "+r"(sv[0].z), "+r"(sv[0].w), "+r"(sv[1].x), "+r"(sv[1].y), "+r"(sv[1].z), "+r"(sv[1].w),
                       "+r"(sv[2].x), "+r"(sv[2].y), "+r"(sv[2].z), "+r"(sv[2].w), "+r"(sv[3].x), "+r"(sv[3].y), "+r"(sv[3].z), "+r"(sv[3].w)
                     : "l"(sp[0]), "l"(sp[1]), "l"(sp[2]), "l"(sp[3]), "r"(tag), "r"(tq) : "memory");
        if (!miss) break;
        wait1 = true;
        if (!early && (b >= NFFN || __all_sync(0xffffffffu, mbar_test(bar_box + (warp >> 1) * 8, 0)))) {
          early = true;
          LOAD_WF(0);
          __syncwarp();
          mbar_arrive_pred(bar_gate, lane0);
        }
        watchdog(n);
      }
      const uint4 v0 = tq < 2 ? own : sv[0], v1 = sv[1], v2 = sv[2], v3 = sv[3];
      PROF(8, ct == PT, 30); STAMP(6);
      float su = (__uint_as_float(v0.x) + __uint_as_float(v1.x)) + (__uint_as_float(v2.x) + __uint_as_float(v3.x));
      float sq = (__uint_as_float(v0.y) + __uint_as_float(v1.y)) + (__uint_as_float(v2.y) + __uint_as_float(v3.y));
      float dt = (__uint_as_float(v0.z) + __uint_as_float(v1.z)) + (__uint_as_float(v2.z) + __uint_as_float(v3.z));
      su += __shfl_xor_sync(0xffffffffu, su, 2); sq += __shfl_xor_sync(0xffffffffu, sq, 2); dt += __shfl_xor_sync(0xffffffffu, dt, 2);
      const float m = su * (1.f / DM);
      float mb, sd;
      ln_scalars(m, fmaxf(sq * (1.f / DM) - m * m, 0.f), mb, sd);
      const float inv = rcp(sd);
      rbest = (dt - mb * A1) * inv + A2;
      mm = pack_bf(mb, mb);
      ih = pack_bf(inv, inv);
      const float lo = inv - bf_lo(ih);
      il = pack_bf(lo, lo);
    }
    int ibest;
    {
      const uint32_t bits = __float_as_uint(rbest);
      const uint32_t key = (((int)bits < 0 ? ~bits : bits | 0x80000000u) & ~0x1ffu) | ((127 - lrow0 - (tq & 1) * 8) << 2) | tag;
      sts1(par + PAR_RED + warp * 4, __reduce_max_sync(0xffffffffu, key));
      PROF(8, ct == PT, 38); STAMP(7);
      uint32_t waited;
      asm volatile("{ .reg .pred p, q; setp.ne.u32 p, %1, 0; barrier.cta.red.or.pred q, 1, 256, p; selp.u32 %0, 1, 0, q; }" : "=r"(waited) : "r"((uint32_t)(wait1 && (wg || CW0))) : "memory");
      const uint4 ka = lds4(par + PAR_RED), kb = lds4(par + PAR_RED + 16);
      const uint32_t k2 = max(max(max(ka.x, ka.y), max(ka.z, ka.w)), max(max(kb.x, kb.y), max(kb.z, kb.w)));
      if (ct == 0 && ((cj & CWM) == 0 || (CWL && !waited))) st_relaxed(g_cand + rb, k2);
      ibest = 127 - ((k2 >> 2) & 127);
    }
    PROF(8, ct == PT, 39); STAMP(8);
    if ((ibest >> 4) == warp) {
      const int src = (ibest & 7) * 4 + ((ibest >> 3) & 1), ch = g * 2;
      const uint32_t cm = __shfl_sync(0xffffffffu, mm, src), ch_ = __shfl_sync(0xffffffffu, ih, src), cl = __shfl_sync(0xffffffffu, il, src);
      const uint32_t xa = res + (ch >> 3) * 16384 + ibest * 128 + (((ch & 7) ^ (ibest & 7)) << 4) + tq * 4;
      const uint32_t x0 = lds1(xa), x1 = lds1(xa ^ 16);
      const uint2 p0 = lds2(par + PAR_T2 + ch * 64 + tq * 16), p1 = lds2(par + PAR_T2 + ch * 64 + 64 + tq * 16);
      uint32_t* dst = g_row + rb * 2 * DM + cj * 128 + ln * 4;
      st_pairs(dst, ln_mod(x0, cm, ch_, cl, p0.x, p0.y), ln_mod(x1, cm, ch_, cl, p1.x, p1.y), tag);
      st_pairs(dst + DM, x0, x1, tag);
      __syncwarp();
    }
    PROF(8, ct == PT, 37); STAMP(9);
    uint32_t wd[64];
    const uint32_t wda = base + unit_of(FT_D, warp >> 1) + (warp & 1) * 8192 + frow * 128 + ((((ln >> 3) & 1) ^ (ln & 7)) << 4);
#define LOAD_WD(f) ldmatrix4t((wda ^ ((((f) >> 1) & 3) * 32)) + ((f) >> 3) * 4096 + ((f) & 1) * 2048, wd[4 * (f)], wd[4 * (f) + 1], wd[4 * (f) + 2], wd[4 * (f) + 3])
    if (!early) {
      if (b < NFFN) mbar_wait(bar_box + (warp >> 1) * 8, 0);
      LOAD_WF(0);
      __syncwarp();
      mbar_arrive_pred(bar_gate, lane0);
    }
    if (b < NFFN) {
      const uint32_t own = base + unit_of(FT_G, warp >> 1) + (warp & 1) * 8192;
      mbar_wait(bar_box + (4 + (warp >> 1)) * 8, 0);
      LOAD_WF(1);
      uint32_t* const ydst = g_ypart + ((size_t)(warp * 16 + tq * 2) * NFFN + b) * 8 + g;
      PROF(8, ct == PT, 31); STAMP(10);
      mbar_wait(bar_box + (8 + (warp >> 1)) * 8, 0);
#pragma unroll
      for (int f = 0; f < WDE; f++) LOAD_WD(f);
      STAMP(11);
      mbar_wait(bar_sel, 0);
      PROF(8, ct == PT, 33); STAMP(12);
      float d[8][4];
#pragma unroll
      for (int i = 0; i < 4; i++) { d[i][0] = 0.f; d[i][1] = 0.f; d[i][2] = 0.f; d[i][3] = 0.f; }
#pragma unroll
      for (int ks = 0; ks < 8; ks++) {
        const uint2 hb = lds2(own + 256 + ks * 32 + tq * 8);
#pragma unroll
        for (int mt = 0; mt < 4; mt++) {
          const int r = ks * 16 + mt * 4;
          mma16816(d[mt], wf[r], wf[r + 1], wf[r + 2], wf[r + 3], hb.x, hb.y);
        }
      }
      sts2(own + (tq * 8 + g) * 8, __float_as_uint((tq & 2) ? ((tq & 1) ? d[1][2] : d[1][0]) : ((tq & 1) ? d[0][2] : d[0][0])),
           __float_as_uint((tq & 2) ? ((tq & 1) ? d[3][2] : d[3][0]) : ((tq & 1) ? d[2][2] : d[2][0])));
      bar_sync(1, 256);
      uint32_t ab[4];
      {
        float G = 0.f, U = 0.f;
        uint2 pv[8];
#pragma unroll
        for (int w8 = 0; w8 < 8; w8++) pv[w8] = lds2(base + ln * 8 + ((FT_G >> (w8 >> 1) * 4) & 15) * UNIT + (w8 & 1) * 8192);
#pragma unroll
        for (int w8 = 0; w8 < 8; w8 += 2) {
          G += __uint_as_float(pv[w8].x) + __uint_as_float(pv[w8 + 1].x);
          U += __uint_as_float(pv[w8].y) + __uint_as_float(pv[w8 + 1].y);
        }
#pragma unroll
        for (int f = WDE; f < 16; f++) LOAD_WD(f);
        const float act = rbf(silu_f(rbf(G))) * rbf(U);
        const uint32_t pk = pack_bf(act, __shfl_down_sync(0xffffffffu, act, 1));
#pragma unroll
        for (int i = 0; i < 4; i++) ab[i] = __shfl_sync(0xffffffffu, pk, i * 8 + tq * 2);
      }
      PROF(8, ct == PT, 34); STAMP(13);
#pragma unroll
      for (int mt = 0; mt < 8; mt++) {
        d[mt][0] = 0.f; d[mt][1] = 0.f; d[mt][2] = 0.f; d[mt][3] = 0.f;
        mma16816(d[mt], wd[mt * 8], wd[mt * 8 + 1], wd[mt * 8 + 2], wd[mt * 8 + 3], ab[0], ab[1]);
        mma16816(d[mt], wd[mt * 8 + 4], wd[mt * 8 + 5], wd[mt * 8 + 6], wd[mt * 8 + 7], ab[2], ab[3]);
      }
#pragma unroll
      for (int i = 0; i < 4; i++) {
        const int m4 = (i >> 1) * 4, e = (i & 1) * 2;
        const float y = (tq & 2) ? ((tq & 1) ? d[m4 + 3][e] : d[m4 + 2][e]) : ((tq & 1) ? d[m4 + 1][e] : d[m4][e]);
        st_relaxed(ydst + (m4 * 2 + (i & 1)) * NFFN * 8, tagf(y, tag));
      }
      PROF(8, ct == PT, 35); STAMP(14);
    }
    mbar_wait(bar_sel, 0);
    mbar_arrive_pred(bar_win, ct == 0);
    const int iwin = lds1(par + PAR_CONST + 60) & 0x7ff;
    const bool cand = (iwin >> 4) == rb * 8 + warp;
    {
      const uint32_t mm0 = __shfl_sync(0xffffffffu, mm, ln & ~1), mm1 = __shfl_sync(0xffffffffu, mm, ln | 1);
      const uint32_t ih0 = __shfl_sync(0xffffffffu, ih, ln & ~1), ih1 = __shfl_sync(0xffffffffu, ih, ln | 1);
      const uint32_t il0 = __shfl_sync(0xffffffffu, il, ln & ~1), il1 = __shfl_sync(0xffffffffu, il, ln | 1);
#pragma unroll 1
      for (int hf = 0; hf < 2; hf++) {
        uint32_t x[16];
#pragma unroll
        for (int i = 0; i < 8; i += 2) ldmatrix4((trow ^ (i << 4)) + hf * 16384, x[2 * i], x[2 * i + 1], x[2 * i + 2], x[2 * i + 3]);
#pragma unroll
        for (int i = 0; i < 8; i++) {
          const uint4 pv = lds4(par + PAR_T2 + (hf * 8 + i) * 64 + tq * 16);
          x[2 * i] = hadd2(x[2 * i], hmul2(pv.z, ln_mod(x[2 * i], mm0, ih0, il0, pv.x, pv.y)));
          x[2 * i + 1] = hadd2(x[2 * i + 1], hmul2(pv.z, ln_mod(x[2 * i + 1], mm1, ih1, il1, pv.x, pv.y)));
        }
#pragma unroll
        for (int i = 0; i < 8; i += 2) stmatrix4((trow ^ (i << 4)) + hf * 16384, x[2 * i], x[2 * i + 1], x[2 * i + 2], x[2 * i + 3]);
      }
      if (!cand) fence_async_smem();
      __syncwarp();
      if (!cand && elect_one()) {
        tma2d_store(&maps.out, res + warp * 2048, cj * 128, rb * 128 + warp * 16);
        tma2d_store(&maps.out, res + 16384 + warp * 2048, cj * 128 + 64, rb * 128 + warp * 16);
        asm volatile("cp.async.bulk.commit_group;" ::: "memory");
      }
    }
    if (cand) {
      const int wrow0 = warp * 16;
#pragma unroll 2
      for (int p = 0; p < 8; p++) {
        const int row = 2 * p + (ln >> 4), ch = ln & 15;
        const uint4 v = lds4(res + (ch >> 3) * 16384 + (wrow0 + row) * 128 + (((ch & 7) ^ (row & 7)) << 4));
        if (rb * 128 + wrow0 + row != iwin) *reinterpret_cast<uint4*>(P.out + (size_t)(rb * 128 + wrow0 + row) * DM + cj * 128 + ch * 8) = v;
      }
    }
    asm volatile("cp.async.bulk.wait_group.read 0;" ::: "memory");
    PROF(8, ct == PT, 11); STAMP(15);
    cluster_wait();
  }
}

typedef CUresult (*EncodeFn)(CUtensorMap*, CUtensorMapDataType, cuuint32_t, void*, const cuuint64_t*, const cuuint64_t*,
                             const cuuint32_t*, const cuuint32_t*, CUtensorMapInterleave, CUtensorMapSwizzle,
                             CUtensorMapL2promotion, CUtensorMapFloatOOBfill);

void map2d(EncodeFn enc, CUtensorMap* m, const void* p, uint64_t rows, uint64_t cols, uint32_t brows) {
  cuuint64_t dims[2] = {cols, rows}, strides[1] = {cols * 2};
  cuuint32_t box[2] = {64, brows}, es[2] = {1, 1};
  enc(m, CU_TENSOR_MAP_DATA_TYPE_BFLOAT16, 2, const_cast<void*>(p), dims, strides, box, es, CU_TENSOR_MAP_INTERLEAVE_NONE,
      CU_TENSOR_MAP_SWIZZLE_128B, CU_TENSOR_MAP_L2_PROMOTION_L2_256B, CU_TENSOR_MAP_FLOAT_OOB_FILL_NONE);
}
void map2d_narrow(EncodeFn enc, CUtensorMap* m, const void* p, uint64_t rows, uint64_t cols, uint32_t brows) {
  cuuint64_t dims[2] = {cols, rows}, strides[1] = {cols * 2};
  cuuint32_t box[2] = {32, brows}, es[2] = {1, 1};
  enc(m, CU_TENSOR_MAP_DATA_TYPE_BFLOAT16, 2, const_cast<void*>(p), dims, strides, box, es, CU_TENSOR_MAP_INTERLEAVE_NONE,
      CU_TENSOR_MAP_SWIZZLE_64B, CU_TENSOR_MAP_L2_PROMOTION_L2_64B, CU_TENSOR_MAP_FLOAT_OOB_FILL_NONE);
}
void map3d(EncodeFn enc, CUtensorMap* m, const void* p, uint64_t rows, uint64_t cols, uint32_t brows, uint32_t nch) {
  cuuint64_t dims[3] = {64, rows, cols / 64}, strides[2] = {cols * 2, 128};
  cuuint32_t box[3] = {64, brows, nch}, es[3] = {1, 1, 1};
  enc(m, CU_TENSOR_MAP_DATA_TYPE_BFLOAT16, 3, const_cast<void*>(p), dims, strides, box, es, CU_TENSOR_MAP_INTERLEAVE_NONE,
      CU_TENSOR_MAP_SWIZZLE_128B, CU_TENSOR_MAP_L2_PROMOTION_L2_256B, CU_TENSOR_MAP_FLOAT_OOB_FILL_NONE);
}

}

extern "C" void kernel_launch(void* const* d_in, const int* in_sizes, int n_in, void* d_out, int out_size) {
  (void)in_sizes; (void)n_in; (void)out_size;
  static EncodeFn enc = nullptr;
  if (!enc) {
    void* fn = nullptr;
    cudaDriverEntryPointQueryResult st;
    cudaGetDriverEntryPoint("cuTensorMapEncodeTiled", &fn, cudaEnableDefault, &st);
    enc = (EncodeFn)fn;
    cudaFuncSetAttribute(fused_kernel, cudaFuncAttributeMaxDynamicSharedMemorySize, SMEM_BYTES);
  }
  Maps maps;
  map2d(enc, &maps.x, d_in[0], SEQ, DM, 128);
  map2d(enc, &maps.out, d_out, SEQ, DM, 16);
  map3d(enc, &maps.wq, d_in[3], DM, NQ, 64, 2);
  map3d(enc, &maps.k, d_in[1], 4 * SK, 128, 128, 1);
  map3d(enc, &maps.v, d_in[2], 4 * SK, 128, 128, 1);
  map3d(enc, &maps.wo, d_in[4], NQ, DM, 64, 2);
  map2d_narrow(enc, &maps.wg, d_in[7], DM, FF, 256);
  map2d_narrow(enc, &maps.wu, d_in[8], DM, FF, 256);
  map3d(enc, &maps.wd, d_in[9], FF, DM, 32, 4);
  map2d_narrow(enc, &maps.wm, d_in[11], DM, NMOD, 256);
  Ptrs p;
  p.x = (const __nv_bfloat16*)d_in[0];
  p.w_r = (const __nv_bfloat16*)d_in[6];
  p.w_gate = (const __nv_bfloat16*)d_in[7];
  p.w_up = (const __nv_bfloat16*)d_in[8];
  p.w_down = (const __nv_bfloat16*)d_in[9];
  p.c = (const __nv_bfloat16*)d_in[10];
  p.w_mod = (const __nv_bfloat16*)d_in[11];
  p.out = (__nv_bfloat16*)d_out;
  fused_kernel<<<NMAIN + NHELP, 384, SMEM_BYTES>>>(maps, p);
}
```

```cpp
#include <cuda_runtime.h>
#include <cuda_bf16.h>
#include <cuda.h>
#include <stdint.h>
#include <type_traits>

#define HD 2
#define HDX 2
#define NRS 8
#define FPACE 3
#define GOST 20
#define WB 3
#define WN 21
#define RES0 17
#define RES1 20
#define HU 32
#define NS1 6
#define PG0 15
#define PSL 0
#define CWM 7
#define WDE 16
#define CWL 1
#define CW0 0
#define ESV 1
#define PPOS 1
#define FB0 0
#define FB2 8
#define OPS 8192
#define OFL 0
#define ODS 8
#define MODUL hfma2
#define ODS1 5
#define SG 1
#define SGB 0
#define VREL 5
#define E0 3

namespace {

constexpr int SEQ = 2048, DM = 1024, NQ = 4096, SK = 2048, WIN = 512, FF = 3584, NMOD = 6144;
constexpr int NMAIN = 128, NHELP = 4, NFFN = 112;
constexpr int NSLOT = 4, SLOT_BYTES = 32768, UNIT = 16384, GST_BYTES = 3 * UNIT;
constexpr uint32_t XT1 = 0xDCBA, XT2 = 0x9687;
constexpr uint32_t WT0 = 0xA741, WT1 = 0x7420, WT2 = 0x4A20;
constexpr uint32_t AT0 = WT1, AT1 = WT2;
constexpr uint32_t QT = 0xDC9696DC;
constexpr int OFF_STAGE = 12 * UNIT;
constexpr uint32_t FT_G = 0x07B3, FT_U = 0xA628, FT_D = 0x5149;
constexpr int OFF_RES = 12 * UNIT;
constexpr int OFF_PAR = 14 * UNIT;
constexpr int OFF_BAR = OFF_PAR + 2528;
constexpr int SMEM_BYTES = OFF_BAR + 544;
static_assert(SMEM_BYTES <= 232448, "smem");

constexpr int PAR_T1 = 0;
constexpr int PAR_T2 = 512;
constexpr int PAR_CONST = 1536;
constexpr int PAR_RED = 1600;
constexpr int PAR_SINK = 2176;

struct Maps {
  CUtensorMap x, wq, k, v, wo, wg, wu, wd, wm, out;
};
struct Ptrs {
  const __nv_bfloat16 *x, *w_r, *c, *w_mod, *w_gate, *w_up, *w_down;
  __nv_bfloat16* out;
};

__device__ __align__(1024) uint8_t g_act[16 * 80 * UNIT];
__device__ __align__(128) uint32_t g_mod[NMOD];
__device__ __align__(128) uint32_t g_modp[2 * 2 * DM];
__device__ __align__(128) uint32_t g_ln1[SEQ * 4];
__device__ __align__(128) uint32_t g_cnt_h[16 * 32];
__device__ __align__(128) uint32_t g_cnt_o[128 * 32];
__device__ __align__(128) uint32_t g_xch[NMAIN * 8 * 256 * 4];
__device__ __align__(128) uint32_t g_stats[8 * SEQ * 4];
__device__ __align__(128) uint32_t g_cand[32];
__device__ __align__(128) uint32_t g_row[16 * 2 * DM];
__device__ __align__(128) uint32_t g_ypart[NMAIN * NFFN * 8];
__device__ uint32_t g_epoch;

__device__ __forceinline__ uint32_t fresh_lane() { uint32_t l; asm volatile("mov.u32 %0, %%laneid;" : "=r"(l)); return l; }
__device__ __forceinline__ uint32_t frag_offset(int warp) {
  const uint32_t l = fresh_lane();
  return ((warp & 3) * 16 + (l & 15)) * 128 + (((l >> 4) ^ (l & 7)) << 4);
}
__device__ __forceinline__ bool elect_one() {
  uint32_t p;
  asm volatile("{ .reg .pred q; elect.sync _|q, 0xffffffff; selp.u32 %0, 1, 0, q; }" : "=r"(p));
  return p;
}
__device__ __forceinline__ uint32_t smem_u32(const void* p) { return (uint32_t)__cvta_generic_to_shared(p); }
__device__ __forceinline__ void mbar_init(uint32_t bar, uint32_t cnt) {
  asm volatile("mbarrier.init.shared::cta.b64 [%0], %1;" ::"r"(bar), "r"(cnt) : "memory");
}
__device__ __forceinline__ void mbar_expect_tx(uint32_t bar, uint32_t bytes) {
  asm volatile("mbarrier.arrive.expect_tx.shared::cta.b64 _, [%0], %1;" ::"r"(bar), "r"(bytes) : "memory");
}
__device__ __forceinline__ void mbar_arrive(uint32_t bar) {
  asm volatile("mbarrier.arrive.shared::cta.b64 _, [%0];" ::"r"(bar) : "memory");
}
__device__ __forceinline__ void mbar_arrive_pred(uint32_t bar, bool p) {
  asm volatile("{ .reg .pred p; setp.ne.b32 p, %1, 0; @p mbarrier.arrive.shared::cta.b64 _, [%0]; }" ::"r"(bar), "r"((int)p) : "memory");
}
__device__ __forceinline__ void mbar_arrive_cl(uint32_t bar, uint32_t off, bool p = true) {
  asm volatile("{ .reg .pred p, q; .reg .b32 a; setp.ne.b32 q, %2, 0; setp.ne.and.b32 p, %0, 0, q; add.u32 a, %0, %1; @p mbarrier.arrive.shared::cluster.b64 _, [a]; }"
               ::"r"(bar), "r"(off), "r"((int)p) : "memory");
}
__device__ __forceinline__ uint32_t mapa(uint32_t addr, uint32_t cta) {
  uint32_t r; asm("mapa.shared::cluster.u32 %0, %1, %2;" : "=r"(r) : "r"(addr), "r"(cta)); return r;
}
__device__ __forceinline__ void cluster_arrive() { asm volatile("barrier.cluster.arrive.relaxed.aligned;" ::: "memory"); }
__device__ __forceinline__ void cluster_wait() { asm volatile("barrier.cluster.wait.aligned;" ::: "memory"); }
__device__ __forceinline__ void watchdog(uint32_t& n) {
}
__device__ __forceinline__ void mbar_wait(uint32_t bar, uint32_t parity) {
  asm volatile("{\n.reg .pred p;\nWAIT_%=:\nmbarrier.try_wait.parity.shared::cta.b64 p, [%0], %1;\n@!p bra WAIT_%=;\n}" ::"r"(bar), "r"(parity) : "memory");
}
__device__ __forceinline__ bool mbar_test(uint32_t bar, uint32_t parity) {
  uint32_t ok;
  asm volatile("{\n.reg .pred p;\nmbarrier.test_wait.parity.shared::cta.b64 p, [%1], %2;\nselp.u32 %0, 1, 0, p;\n}" : "=r"(ok) : "r"(bar), "r"(parity) : "memory");
  return ok;
}
__device__ __forceinline__ uint64_t l2_stream() {
  uint64_t f; asm("createpolicy.fractional.L2::evict_first.b64 %0, 1.0;" : "=l"(f)); return f;
}
__device__ __forceinline__ void tma2d(uint32_t dst, const CUtensorMap* m, int c0, int c1, uint32_t bar) {
  asm volatile("cp.async.bulk.tensor.2d.shared::cluster.global.mbarrier::complete_tx::bytes.L2::cache_hint [%0], [%1, {%3, %4}], [%2], %5;"
               ::"r"(dst), "l"(m), "r"(bar), "r"(c0), "r"(c1), "l"(l2_stream()) : "memory");
}
__device__ __forceinline__ void bulk_load(uint32_t dst, const void* src, uint32_t bytes, uint32_t bar) {
  asm volatile("cp.async.bulk.shared::cluster.global.mbarrier::complete_tx::bytes [%0], [%1], %2, [%3];" ::"r"(dst), "l"(src), "r"(bytes), "r"(bar) : "memory");
}
__device__ __forceinline__ void bulk_load_stream(uint32_t dst, const void* src, uint32_t bytes, uint32_t bar) {
  asm volatile("cp.async.bulk.shared::cluster.global.mbarrier::complete_tx::bytes.L2::cache_hint [%0], [%1], %2, [%3], %4;"
               ::"r"(dst), "l"(src), "r"(bytes), "r"(bar), "l"(l2_stream()) : "memory");
}
__device__ __forceinline__ void tma2d_store(const CUtensorMap* m, uint32_t src, int c0, int c1) {
  asm volatile("cp.async.bulk.tensor.2d.global.shared::cta.bulk_group [%0, {%2, %3}], [%1];" ::"l"(m), "r"(src), "r"(c0), "r"(c1) : "memory");
}
__device__ __forceinline__ void bulk_store(void* dst, uint32_t src, uint32_t bytes) {
  asm volatile("cp.async.bulk.global.shared::cta.bulk_group [%0], [%1], %2;" ::"l"(dst), "r"(src), "r"(bytes) : "memory");
}
__device__ __forceinline__ uint32_t unit_of(uint32_t table, uint32_t i) { return ((table >> (i * 4)) & 15) * UNIT; }
__device__ __forceinline__ void tma3d(uint32_t dst, const CUtensorMap* m, int c0, int c1, int c2, uint32_t bar) {
  asm volatile("cp.async.bulk.tensor.3d.shared::cluster.global.mbarrier::complete_tx::bytes.L2::cache_hint [%0], [%1, {%3, %4, %5}], [%2], %6;"
               ::"r"(dst), "l"(m), "r"(bar), "r"(c0), "r"(c1), "r"(c2), "l"(l2_stream()) : "memory");
}
template <bool STREAM>
__device__ __forceinline__ void tma3d_mc(uint32_t dst, const CUtensorMap* m, int c0, int c1, int c2, uint32_t bar) {
  if (STREAM)
    asm volatile("cp.async.bulk.tensor.3d.shared::cluster.global.mbarrier::complete_tx::bytes.multicast::cluster.L2::cache_hint [%0], [%1, {%3, %4, %5}], [%2], %6, %7;"
                 ::"r"(dst), "l"(m), "r"(bar), "r"(c0), "r"(c1), "r"(c2), "h"((uint16_t)3), "l"(l2_stream()) : "memory");
  else
    asm volatile("cp.async.bulk.tensor.3d.shared::cluster.global.mbarrier::complete_tx::bytes.multicast::cluster [%0], [%1, {%3, %4, %5}], [%2], %6;"
                 ::"r"(dst), "l"(m), "r"(bar), "r"(c0), "r"(c1), "r"(c2), "h"((uint16_t)3) : "memory");
}
__device__ __forceinline__ void prefetch_map(const CUtensorMap* m) {
  asm volatile("prefetch.tensormap [%0];" ::"l"(m) : "memory");
}
__device__ __forceinline__ void fence_async() { asm volatile("fence.proxy.async.global;" ::: "memory"); }
__device__ __forceinline__ void fence_async_smem() { asm volatile("fence.proxy.async.shared::cta;" ::: "memory"); }
__device__ __forceinline__ void bar_sync(int id, int n) { asm volatile("bar.sync %0, %1;" ::"r"(id), "r"(n) : "memory"); }
__device__ __forceinline__ void bar_arrive(int id, int n) { asm volatile("bar.arrive %0, %1;" ::"r"(id), "r"(n) : "memory"); }
__device__ __forceinline__ void wg_fence() { asm volatile("wgmma.fence.sync.aligned;" ::: "memory"); }
__device__ __forceinline__ void wg_commit() { asm volatile("wgmma.commit_group.sync.aligned;" ::: "memory"); }
template <int N> __device__ __forceinline__ void wg_wait() { asm volatile("wgmma.wait_group.sync.aligned %0;" ::"n"(N) : "memory"); }
__device__ __forceinline__ uint64_t make_desc(uint32_t addr, uint32_t lbo, uint32_t sbo) {
  return (uint64_t)((addr & 0x3FFFF) >> 4) | ((uint64_t)(lbo >> 4) << 16) | ((uint64_t)(sbo >> 4) << 32) | (1ull << 62);
}
__device__ __forceinline__ uint32_t ld_relaxed(const uint32_t* p) {
  uint32_t v; asm volatile("ld.relaxed.gpu.global.u32 %0, [%1];" : "=r"(v) : "l"(p) : "memory"); return v;
}
__device__ __forceinline__ uint32_t ld_acquire(const uint32_t* p) {
  uint32_t v; asm volatile("ld.acquire.gpu.global.u32 %0, [%1];" : "=r"(v) : "l"(p) : "memory"); return v;
}
__device__ __forceinline__ uint4 ld_relaxed4(const uint32_t* p) {
  uint4 v; asm volatile("ld.relaxed.gpu.global.v4.u32 {%0,%1,%2,%3}, [%4];" : "=r"(v.x), "=r"(v.y), "=r"(v.z), "=r"(v.w) : "l"(p) : "memory"); return v;
}
__device__ __forceinline__ uint2 ld_relaxed2(const uint32_t* p) {
  uint2 v; asm volatile("ld.relaxed.gpu.global.v2.u32 {%0,%1}, [%2];" : "=r"(v.x), "=r"(v.y) : "l"(p) : "memory"); return v;
}
__device__ __forceinline__ void st_relaxed(uint32_t* p, uint32_t v) {
  asm volatile("st.relaxed.gpu.global.u32 [%0], %1;" ::"l"(p), "r"(v) : "memory");
}
__device__ __forceinline__ void st_relaxed2(uint32_t* p, uint32_t a, uint32_t b) {
  asm volatile("st.relaxed.gpu.global.v2.u32 [%0], {%1,%2};" ::"l"(p), "r"(a), "r"(b) : "memory");
}
__device__ __forceinline__ void st_relaxed4(uint32_t* p, uint32_t a, uint32_t b, uint32_t c, uint32_t d) {
  asm volatile("st.relaxed.gpu.global.v4.u32 [%0], {%1,%2,%3,%4};" ::"l"(p), "r"(a), "r"(b), "r"(c), "r"(d) : "memory");
}
__device__ __forceinline__ void st_b128(uint32_t* p, uint32_t a, uint32_t b, uint32_t c, uint32_t d) {
  asm volatile("{ .reg .b64 u, v; .reg .b128 w; mov.b64 u, {%1, %2}; mov.b64 v, {%3, %4}; mov.b128 w, {u, v}; st.relaxed.gpu.global.b128 [%0], w; }"
               ::"l"(p), "r"(a), "r"(b), "r"(c), "r"(d) : "memory");
}
__device__ __forceinline__ uint4 ld_b128(const uint32_t* p) {
  uint4 r;
  asm volatile("{ .reg .b64 u, v; .reg .b128 w; ld.relaxed.gpu.global.b128 w, [%4]; mov.b128 {u, v}, w; mov.b64 {%0, %1}, u; mov.b64 {%2, %3}, v; }"
               : "=r"(r.x), "=r"(r.y), "=r"(r.z), "=r"(r.w) : "l"(p) : "memory");
  return r;
}
__device__ __forceinline__ void st_pairs(uint32_t* p, uint32_t a, uint32_t b, uint32_t tag) {
  asm volatile("{ .reg .b64 u, v; mov.b64 u, {%1, %3}; mov.b64 v, {%2, %3}; st.relaxed.gpu.global.v2.b64 [%0], {u, v}; }"
               ::"l"(p), "r"(a), "r"(b), "r"(tag) : "memory");
}
__device__ __forceinline__ uint4 ld_pairs(const uint32_t* p) {
  uint4 v;
  asm volatile("{ .reg .b64 u, v; ld.relaxed.gpu.global.v2.b64 {u, v}, [%4]; mov.b64 {%0, %1}, u; mov.b64 {%2, %3}, v; }"
               : "=r"(v.x), "=r"(v.y), "=r"(v.z), "=r"(v.w) : "l"(p) : "memory");
  return v;
}
__device__ __forceinline__ uint2 ld_pair(const uint32_t* p) {
  uint2 v;
  asm volatile("{ .reg .b64 u; ld.relaxed.gpu.global.b64 u, [%2]; mov.b64 {%0, %1}, u; }" : "=r"(v.x), "=r"(v.y) : "l"(p) : "memory");
  return v;
}
__device__ __forceinline__ void red_release(uint32_t* p, uint32_t v) {
  asm volatile("red.release.gpu.global.add.u32 [%0], %1;" ::"l"(p), "r"(v) : "memory");
}
__device__ __forceinline__ uint32_t ldg_nc1(const void* p) {
  uint32_t v;
  asm volatile("ld.global.nc.u32 %0, [%1];" : "=r"(v) : "l"(p));
  return v;
}
__device__ __forceinline__ uint4 ldg_nc4(const void* p) {
  uint4 v; asm volatile("ld.global.nc.L1::no_allocate.v4.u32 {%0,%1,%2,%3}, [%4];" : "=r"(v.x), "=r"(v.y), "=r"(v.z), "=r"(v.w) : "l"(p)); return v;
}
__device__ __forceinline__ uint4 ldg_stream4(const void* p) {
  uint4 v;
  asm volatile("ld.global.nc.L1::no_allocate.L2::cache_hint.v4.u32 {%0,%1,%2,%3}, [%4], %5;" : "=r"(v.x), "=r"(v.y), "=r"(v.z), "=r"(v.w) : "l"(p), "l"(l2_stream()));
  return v;
}
__device__ __forceinline__ void stg4(void* p, uint4 v) {
  asm volatile("st.global.v4.u32 [%0], {%1,%2,%3,%4};" ::"l"(p), "r"(v.x), "r"(v.y), "r"(v.z), "r"(v.w) : "memory");
}
__device__ __forceinline__ void wait_counter(const uint32_t* p, uint32_t target) {
  uint32_t n = 0;
  while (__any_sync(0xffffffffu, (int)(ld_acquire(p) - target) < 0)) { watchdog(n); }
}
__device__ __forceinline__ uint32_t tagf(float v, uint32_t tag) { return (__float_as_uint(v) & ~3u) | tag; }
__device__ __forceinline__ bool tag_ok(uint4 v, uint32_t tag) { return (((v.x ^ tag) | (v.y ^ tag) | (v.z ^ tag) | (v.w ^ tag)) & 3u) == 0; }
__device__ __forceinline__ float untag_sum(uint32_t a, uint32_t b) { return __uint_as_float(a & ~3u) + __uint_as_float(b & ~3u); }
__device__ __forceinline__ uint4 poll4(const uint32_t* p, uint32_t tag) {
  uint4 v = ld_relaxed4(p);
  uint32_t n = 0;
  while (!__all_sync(0xffffffffu, tag_ok(v, tag))) { v = ld_relaxed4(p); watchdog(n); }
  return v;
}
__device__ __forceinline__ float bf_lo(uint32_t v) { return __uint_as_float(v << 16); }
__device__ __forceinline__ float bf_hi(uint32_t v) { return __uint_as_float(v & 0xffff0000u); }
__device__ __forceinline__ uint32_t pack_bf(float lo, float hi) {
  uint32_t r; asm("cvt.rn.bf16x2.f32 %0, %1, %2;" : "=r"(r) : "f"(hi), "f"(lo)); return r;
}
__device__ __forceinline__ float rbf(float v) { return __uint_as_float(pack_bf(0.f, v) & 0xffff0000u); }
__device__ __forceinline__ uint32_t hmul2(uint32_t a, uint32_t b) {
  uint32_t r; asm("mul.rn.bf16x2 %0, %1, %2;" : "=r"(r) : "r"(a), "r"(b)); return r;
}
__device__ __forceinline__ uint32_t hadd2(uint32_t a, uint32_t b) {
  uint32_t r; asm("add.rn.bf16x2 %0, %1, %2;" : "=r"(r) : "r"(a), "r"(b)); return r;
}
__device__ __forceinline__ uint32_t hsub2(uint32_t a, uint32_t b) {
  uint32_t r; asm("sub.rn.bf16x2 %0, %1, %2;" : "=r"(r) : "r"(a), "r"(b)); return r;
}
__device__ __forceinline__ uint32_t hmax2(uint32_t a, uint32_t b) {
  uint32_t r; asm("max.bf16x2 %0, %1, %2;" : "=r"(r) : "r"(a), "r"(b)); return r;
}
__device__ __forceinline__ float rcp(float x) { float r; asm("rcp.approx.ftz.f32 %0, %1;" : "=f"(r) : "f"(x)); return r; }
__device__ __forceinline__ float ex2(float x) { float r; asm("ex2.approx.ftz.f32 %0, %1;" : "=f"(r) : "f"(x)); return r; }
__device__ __forceinline__ void stmatrix4(uint32_t addr, uint32_t a, uint32_t b, uint32_t c, uint32_t d) {
  asm volatile("stmatrix.sync.aligned.m8n8.x4.shared.b16 [%0], {%1,%2,%3,%4};" ::"r"(addr), "r"(a), "r"(b), "r"(c), "r"(d) : "memory");
}
__device__ __forceinline__ void ldmatrix4(uint32_t addr, uint32_t& a, uint32_t& b, uint32_t& c, uint32_t& d) {
  asm volatile("ldmatrix.sync.aligned.m8n8.x4.shared.b16 {%0,%1,%2,%3}, [%4];" : "=r"(a), "=r"(b), "=r"(c), "=r"(d) : "r"(addr) : "memory");
}
__device__ __forceinline__ void ldmatrix4t(uint32_t addr, uint32_t& a, uint32_t& b, uint32_t& c, uint32_t& d) {
  asm volatile("ldmatrix.sync.aligned.m8n8.x4.trans.shared.b16 {%0,%1,%2,%3}, [%4];" : "=r"(a), "=r"(b), "=r"(c), "=r"(d) : "r"(addr) : "memory");
}
__device__ __forceinline__ void mma16816(float (&d)[4], uint32_t a0, uint32_t a1, uint32_t a2, uint32_t a3, uint32_t b0, uint32_t b1) {
  asm volatile("mma.sync.aligned.m16n8k16.row.col.f32.bf16.bf16.f32 {%0,%1,%2,%3}, {%4,%5,%6,%7}, {%8,%9}, {%0,%1,%2,%3};"
               : "+f"(d[0]), "+f"(d[1]), "+f"(d[2]), "+f"(d[3]) : "r"(a0), "r"(a1), "r"(a2), "r"(a3), "r"(b0), "r"(b1));
}
__device__ __forceinline__ void sts1(uint32_t a, uint32_t v) { asm volatile("st.shared.u32 [%0], %1;" ::"r"(a), "r"(v) : "memory"); }
__device__ __forceinline__ uint4 lds4(uint32_t a) {
  uint4 v; asm volatile("ld.shared.v4.u32 {%0,%1,%2,%3}, [%4];" : "=r"(v.x), "=r"(v.y), "=r"(v.z), "=r"(v.w) : "r"(a) : "memory"); return v;
}
__device__ __forceinline__ uint2 lds2(uint32_t a) {
  uint2 v; asm volatile("ld.shared.v2.u32 {%0,%1}, [%2];" : "=r"(v.x), "=r"(v.y) : "r"(a) : "memory"); return v;
}
__device__ __forceinline__ uint32_t lds1(uint32_t a) {
  uint32_t v; asm volatile("ld.shared.u32 %0, [%1];" : "=r"(v) : "r"(a) : "memory"); return v;
}
__device__ __forceinline__ void sts2(uint32_t a, uint32_t x, uint32_t y) { asm volatile("st.shared.v2.u32 [%0], {%1,%2};" ::"r"(a), "r"(x), "r"(y) : "memory"); }
__device__ __forceinline__ void sts4(uint32_t a, uint4 v) {
  asm volatile("st.shared.v4.u32 [%0], {%1,%2,%3,%4};" ::"r"(a), "r"(v.x), "r"(v.y), "r"(v.z), "r"(v.w) : "memory");
}
__device__ __forceinline__ float silu_f(float v) { return __fdividef(v, 1.f + __expf(-v)); }
__device__ __forceinline__ uint32_t hfma2(uint32_t a, uint32_t b, uint32_t c) {
  uint32_t r; asm("fma.rn.bf16x2 %0, %1, %2, %3;" : "=r"(r) : "r"(a), "r"(b), "r"(c)); return r;
}
__device__ __forceinline__ void split_inv(float sd, uint32_t& ih, uint32_t& il) {
  const float inv = rcp(sd);
  ih = pack_bf(inv, inv);
  const float lo = inv - bf_lo(ih);
  il = pack_bf(lo, lo);
}
__device__ __forceinline__ uint32_t ln_norm(uint32_t x, uint32_t mean2, uint32_t ih, uint32_t il) {
  const uint32_t d = hsub2(x, mean2);
  return hfma2(d, ih, hmul2(d, il));
}
__device__ __forceinline__ uint32_t modul(uint32_t n, uint32_t c1, uint32_t sh) { return hadd2(hmul2(n, c1), sh); }
__device__ __forceinline__ uint32_t ln_mod(uint32_t x, uint32_t mean2, uint32_t ih, uint32_t il, uint32_t c1, uint32_t sh) {
  return modul(ln_norm(x, mean2, ih, il), c1, sh);
}

#define R8(a, i) "+f"(a[i]), "+f"(a[i + 1]), "+f"(a[i + 2]), "+f"(a[i + 3]), "+f"(a[i + 4]), "+f"(a[i + 5]), "+f"(a[i + 6]), "+f"(a[i + 7])
#define D64 "{%0,%1,%2,%3,%4,%5,%6,%7,%8,%9,%10,%11,%12,%13,%14,%15,%16,%17,%18,%19,%20,%21,%22,%23,%24,%25,%26,%27,%28,%29,%30,%31," \
            "%32,%33,%34,%35,%36,%37,%38,%39,%40,%41,%42,%43,%44,%45,%46,%47,%48,%49,%50,%51,%52,%53,%54,%55,%56,%57,%58,%59,%60,%61,%62,%63}"
template <int TB>
__device__ __forceinline__ void mma_ss(float (&d)[64], uint64_t da, uint64_t db, int sc) {
  asm volatile("{\n.reg .pred p;\nsetp.ne.b32 p, %66, 0;\n"
               "wgmma.mma_async.sync.aligned.m64n128k16.f32.bf16.bf16 " D64 ", %64, %65, p, 1, 1, 0, %67;\n}"
               : R8(d, 0), R8(d, 8), R8(d, 16), R8(d, 24), R8(d, 32), R8(d, 40), R8(d, 48), R8(d, 56)
               : "l"(da), "l"(db), "r"(sc), "n"(TB));
}
template <int TB>
__device__ __forceinline__ void mma_rs(float (&d)[64], uint32_t a0, uint32_t a1, uint32_t a2, uint32_t a3, uint64_t db, int sc) {
  asm volatile("{\n.reg .pred p;\nsetp.ne.b32 p, %69, 0;\n"
               "wgmma.mma_async.sync.aligned.m64n128k16.f32.bf16.bf16 " D64 ", {%64,%65,%66,%67}, %68, p, 1, 1, %70;\n}"
               : R8(d, 0), R8(d, 8), R8(d, 16), R8(d, 24), R8(d, 32), R8(d, 40), R8(d, 48), R8(d, 56)
               : "r"(a0), "r"(a1), "r"(a2), "r"(a3), "l"(db), "r"(sc), "n"(TB));
}
#define D128 "{%0,%1,%2,%3,%4,%5,%6,%7,%8,%9,%10,%11,%12,%13,%14,%15,%16,%17,%18,%19,%20,%21,%22,%23,%24,%25,%26,%27,%28,%29,%30,%31," \
             "%32,%33,%34,%35,%36,%37,%38,%39,%40,%41,%42,%43,%44,%45,%46,%47,%48,%49,%50,%51,%52,%53,%54,%55,%56,%57,%58,%59,%60,%61,%62,%63," \
             "%64,%65,%66,%67,%68,%69,%70,%71,%72,%73,%74,%75,%76,%77,%78,%79,%80,%81,%82,%83,%84,%85,%86,%87,%88,%89,%90,%91,%92,%93,%94,%95," \
             "%96,%97,%98,%99,%100,%101,%102,%103,%104,%105,%106,%107,%108,%109,%110,%111,%112,%113,%114,%115,%116,%117,%118,%119,%120,%121,%122,%123,%124,%125,%126,%127}"
#define R128(d, e) R8(d, 0), R8(d, 8), R8(d, 16), R8(d, 24), R8(d, 32), R8(d, 40), R8(d, 48), R8(d, 56), \
                   R8(e, 0), R8(e, 8), R8(e, 16), R8(e, 24), R8(e, 32), R8(e, 40), R8(e, 48), R8(e, 56)
__device__ __forceinline__ void mma256_ss(float (&d)[64], float (&e)[64], uint64_t da, uint64_t db, int sc) {
  asm volatile("{\n.reg .pred p;\nsetp.ne.b32 p, %130, 0;\n"
               "wgmma.mma_async.sync.aligned.m64n256k16.f32.bf16.bf16 " D128 ", %128, %129, p, 1, 1, 0, 1;\n}"
               : R128(d, e) : "l"(da), "l"(db), "r"(sc));
}
__device__ __forceinline__ void mma256_rs(float (&d)[64], float (&e)[64], uint32_t a0, uint32_t a1, uint32_t a2, uint32_t a3, uint64_t db) {
  asm volatile("{\n.reg .pred p;\nsetp.ne.b32 p, 1, 0;\n"
               "wgmma.mma_async.sync.aligned.m64n256k16.f32.bf16.bf16 " D128 ", {%128,%129,%130,%131}, %132, p, 1, 1, 1;\n}"
               : R128(d, e) : "r"(a0), "r"(a1), "r"(a2), "r"(a3), "l"(db));
}
template <int N> __device__ __forceinline__ void keep(float (&a)[N]) {
#pragma unroll
  for (int i = 0; i < N; i++) asm volatile("" : "+f"(a[i])::"memory");
}
template <int N> __device__ __forceinline__ void keep(uint32_t (&a)[N]) {
#pragma unroll
  for (int i = 0; i < N; i++) asm volatile("" : "+r"(a[i])::"memory");
}

#define STAMP(idx) do {} while (0)
#define PROF(grp, cond, idx) do {} while (0)

constexpr float SCL2 = 1.4426950408889634f * 0.08838834764831845f;

__device__ __forceinline__ void pack_p(const float (&s)[64], uint32_t (&p)[32]) {
#pragma unroll
  for (int i = 0; i < 32; i++) p[i] = pack_bf(s[2 * i], s[2 * i + 1]);
}

__device__ __forceinline__ void issue_qk(float (&s)[64], uint32_t q0, uint32_t q1, uint32_t kslot) {
  const uint64_t db = make_desc(kslot, 16, 1024), da0 = make_desc(q0, 16, 1024), da1 = make_desc(q1, 16, 1024);
#pragma unroll
  for (int kk = 0; kk < 8; kk++) mma_ss<0>(s, (kk < 4 ? da0 : da1) + (kk & 3) * 2, db + (kk >> 2) * 1024 + (kk & 3) * 2, kk != 0);
}
__device__ __forceinline__ void issue_pv(float (&o)[64], uint32_t (&p)[32], uint32_t vslot, int acc) {
  uint64_t db = make_desc(vslot, 16384, 1024);
#pragma unroll
  for (int kk = 0; kk < 8; kk++)
    mma_rs<1>(o, p[4 * kk], p[4 * kk + 1], p[4 * kk + 2], p[4 * kk + 3], db + kk * 128, kk == 0 ? acc : 1);
}

template <int H>
__device__ __forceinline__ void store_chunk(const float (&a)[64], uint32_t addr) {
#pragma unroll
  for (int i = 8 * H; i < 8 * H + 8; i += 2)
    stmatrix4(addr ^ ((i & 7) << 4), pack_bf(a[4 * i], a[4 * i + 1]), pack_bf(a[4 * i + 2], a[4 * i + 3]),
              pack_bf(a[4 * i + 4], a[4 * i + 5]), pack_bf(a[4 * i + 6], a[4 * i + 7]));
}
template <int H>
__device__ __forceinline__ void store_chunk(const float (&a)[64], float i0, float i1, uint32_t addr) {
#pragma unroll
  for (int i = 8 * H; i < 8 * H + 8; i += 2)
    stmatrix4(addr ^ ((i & 7) << 4), pack_bf(a[4 * i] * i0, a[4 * i + 1] * i0), pack_bf(a[4 * i + 2] * i1, a[4 * i + 3] * i1),
              pack_bf(a[4 * i + 4] * i0, a[4 * i + 5] * i0), pack_bf(a[4 * i + 6] * i1, a[4 * i + 7] * i1));
}
__device__ __forceinline__ float inv_quad_sum(float l) {
  l += __shfl_xor_sync(0xffffffffu, l, 1);
  l += __shfl_xor_sync(0xffffffffu, l, 2);
  return rcp(l);
}

__device__ __forceinline__ void ln_scalars(float mean, float var, float& mb, float& sd) {
  mb = rbf(mean);
  float r; asm("sqrt.approx.ftz.f32 %0, %1;" : "=f"(r) : "f"(rbf(rbf(var) + 1e-5f)));
  sd = rbf(r);
}

__global__ void __cluster_dims__(2, 1, 1) __launch_bounds__(384, 1) fused_kernel(const __grid_constant__ Maps maps, const Ptrs P) {
  extern __shared__ __align__(1024) uint8_t smem_raw[];
  const uint32_t base = smem_u32(smem_raw);
  const int tid = threadIdx.x, lane = tid & 31;
  const int warp = __shfl_sync(0xffffffffu, tid >> 5, 0);
  const int b = blockIdx.x;
  PROF(31, tid == 0, 0);

  if (b >= NMAIN) {
    float* sc = reinterpret_cast<float*>(smem_raw);
    float* red = sc + DM;
    for (int k = tid; k < DM; k += 384) sc[k] = rbf(silu_f(__bfloat162float(P.c[k])));
    __syncthreads();
    if (tid < 256) {
      const int col = 2048 + (b - NMAIN) * 1024 + (tid & 127) * 8, r0 = (tid >> 7) * 512;
      float acc[8];
#pragma unroll
      for (int e = 0; e < 8; e++) acc[e] = 0.f;
#pragma unroll 1
      for (int r = r0; r < r0 + 512; r += HU) {
        uint4 w[HU];
#pragma unroll
        for (int u = 0; u < HU; u++) w[u] = ldg_stream4(P.w_mod + (size_t)(r + u) * NMOD + col);
#pragma unroll
        for (int u = 0; u < HU; u++) {
          float s = sc[r + u];
          acc[0] += s * bf_lo(w[u].x); acc[1] += s * bf_hi(w[u].x); acc[2] += s * bf_lo(w[u].y); acc[3] += s * bf_hi(w[u].y);
          acc[4] += s * bf_lo(w[u].z); acc[5] += s * bf_hi(w[u].z); acc[6] += s * bf_lo(w[u].w); acc[7] += s * bf_hi(w[u].w);
        }
      }
      if (tid >= 128) {
#pragma unroll
        for (int e = 0; e < 8; e++) red[(tid & 127) * 8 + e] = acc[e];
      }
      const uint32_t tag = ld_relaxed(&g_epoch) % 3 + 1;
      bar_sync(1, 256);
      if (tid < 128) {
        uint32_t o[8];
#pragma unroll
        for (int e = 0; e < 8; e++) o[e] = __float_as_uint(rbf(acc[e] + red[tid * 8 + e])) | tag;
        st_relaxed4(g_mod + col, o[0], o[1], o[2], o[3]);
        st_relaxed4(g_mod + col + 4, o[4], o[5], o[6], o[7]);
        const uint4 wr = ldg_nc4(P.w_r + tid * 8);
        const uint32_t wv[4] = {wr.x, wr.y, wr.z, wr.w};
        float dsum = 0.f;
#pragma unroll
        for (int e = 0; e < 8; e++) {
          const float m = bf_hi(o[e]);
          dsum += (b == NMAIN + 2 ? rbf(1.f + m) : m) * ((e & 1) ? bf_hi(wv[e >> 1]) : bf_lo(wv[e >> 1]));
        }
#pragma unroll
        for (int k = 16; k > 0; k >>= 1) dsum += __shfl_xor_sync(0xffffffffu, dsum, k);
        if (lane == 0) st_relaxed(g_mod + (b - NMAIN) * 4 + warp, tagf(dsum, tag));
      }
    }
    PROF(2, tid == 0, 1);
    return;
  }

  const int rank = b & 1;
  const int rb = ((b >> 4) << 1) | rank, cj = (b >> 1) & 7;
  const uint32_t bfull = base + OFF_BAR, bempty = bfull + NSLOT * 8;
  const uint32_t gfull = bempty + NSLOT * 8, gempty = gfull + 32;
  const uint32_t bar_ofull = gempty + 32;
  const uint32_t bar_ofree = bar_ofull + 32;
  const uint32_t bar_par = bar_ofree + 32;
  const uint32_t bar_mod = bar_par + 8;
  const uint32_t bar_pread = bar_mod + 8;
  const uint32_t bar_xres = bar_pread + 8;
  const uint32_t bar_ring = bar_xres + 8;
  const uint32_t bar_box = bar_ring + 24;
  const uint32_t bar_go = bar_box + 96;
  const uint32_t bar_go2 = bar_go + 16;
  const uint32_t bar_cnt = bar_go + 24;
  const uint32_t xfull = bar_go + 40, xempty = xfull + 32;
  const uint32_t bar_hw = xempty + 32, bar_hx = bar_hw + 8;
  const uint32_t bar_hpub = bar_hx + 16;
  const uint32_t bar_win = bar_hpub + 16;
  const uint32_t bar_rx = bar_win + 8;
  const uint32_t bar_sel = bar_rx + 8;
  const uint32_t bar_gate = bar_sel + 8;
  const uint32_t bar_rel = bar_gate + 8;
  const uint32_t bar_od = bar_rel + 8;
  const uint32_t bar_res = bar_go + 8;
  const uint32_t stage = base + OFF_STAGE, par = base + OFF_PAR;

  if (warp == 8 && elect_one()) {
    for (int s = 0; s < NSLOT; s++) { mbar_init(bfull + s * 8, 1); mbar_init(bempty + s * 8, 16); }
    for (int s = 0; s < 4; s++) { mbar_init(gfull + s * 8, 1); mbar_init(gempty + s * 8, 16); mbar_init(xfull + s * 8, 1); mbar_init(xempty + s * 8, 8); mbar_init(bar_ofree + s * 8, 1); mbar_init(bar_ofull + s * 8, 128); }
    mbar_init(bar_par, 64); mbar_init(bar_mod, 256); mbar_init(bar_pread, 2); mbar_init(bar_xres, 1);
    mbar_init(bar_ring, 8); mbar_init(bar_ring + 8, 8); mbar_init(bar_ring + 16, 8);
    mbar_init(bar_go, 1); mbar_init(bar_go2, 1); mbar_init(bar_cnt, 1); mbar_init(bar_cnt + 8, 1); mbar_init(bar_hpub, 8); mbar_init(bar_hpub + 8, 8); mbar_init(bar_res, 1); mbar_init(bar_win, 1); mbar_init(bar_rx, 1); mbar_init(bar_sel, 64); mbar_init(bar_gate, 8); mbar_init(bar_rel, 8); mbar_init(bar_od, 1);
    for (int s = 0; s < 12; s++) mbar_init(bar_box + s * 8, 1);
    asm volatile("fence.mbarrier_init.release.cluster;" ::: "memory");
    prefetch_map(&maps.x); prefetch_map(&maps.wq); prefetch_map(&maps.k); prefetch_map(&maps.v);
  }
  if (warp == 9 && elect_one()) {
    mbar_init(bar_hw, 1); mbar_init(bar_hx, 1); mbar_init(bar_hx + 8, 1);
    asm volatile("fence.mbarrier_init.release.cluster;" ::: "memory");
    mbar_expect_tx(bar_hw, 32768);
    mbar_expect_tx(bar_hx, 16384);
    mbar_expect_tx(bar_hx + 8, 16384);
    const __nv_bfloat16* xs = P.x + (size_t)(rb * 128 + cj * 16) * DM;
    bulk_load(base + 2 * GST_BYTES, xs, 16384, bar_hx);
    tma2d(stage, &maps.wm, (b >> 1) * 32, rank * 512, bar_hw);
    tma2d(stage + 16384, &maps.wm, (b >> 1) * 32, rank * 512 + 256, bar_hw);
    bulk_load(base + 3 * GST_BYTES, xs + 8 * DM, 16384, bar_hx + 8);
  }
  cluster_arrive();

  if (warp >= 8) {
    asm volatile("setmaxnreg.dec.sync.aligned.u32 40;");
    if (warp < 10) bar_arrive(1, 320);
    const uint32_t epoch = ld_relaxed(&g_epoch);
    cluster_wait();
    if (warp == 8) {
      const int kvrow = (cj >> 1) * SK + (SK - WIN);
      int wch = cj * 8 + rank * 2;
#pragma unroll 1
      for (int ps = 0; ps < 3; ps++) {
        const CUtensorMap* mw = ps == 2 ? &maps.wo : &maps.wq;
        const uint32_t xt = ps == 1 ? XT1 : XT2, wt = ps == 0 ? WT0 : (ps == 1 ? WT1 : WT2);
        const int nst = ps == 2 ? 32 : 16;
#pragma unroll 1
        for (int i = 0; i < nst; i++) {
          const uint32_t bf = gfull + (i & 3) * 8;
          const int kt = ps == 2 ? (((cj & 1) * 4 + ((i >> 1) & 3)) * 4 + (i >> 3)) * 2 + (i & 1) : (i + (ps ? 0 : b & 14)) & 15;
          const uint32_t wd = base + unit_of(wt, i & 3) + rank * UNIT, xd = base + unit_of(xt, i & 3);
          const uint8_t* xs = g_act + (uint32_t)(rb * 80 + (ps - 1) * 16 + kt) * UNIT;
          if (ps == 0 && i == HD) mbar_wait(bar_mod, 0);
          const bool xfirst = ps && i < 2;
          if (ps == 2 && i == 0) mbar_wait(bar_ofree + 24, 0);
          if (i == 0) fence_async();
          mbar_wait(gempty + (i & 3) * 8, ((i >> 2) & 1) ^ 1);
          if (elect_one()) {
            mbar_expect_tx(bf, ps ? GST_BYTES : 2 * UNIT);
            if (xfirst) bulk_load_stream(xd, xs, UNIT, bf);
          }
          if (ps && i < 4) mbar_wait(bempty + i * 8, 1);
          if (elect_one()) tma3d_mc<true>(wd, mw, 0, (i == 31 ? kt ^ (rank * 32) : kt) * 64, i == 31 ? cj * 2 : wch, bf);
          if (ps) {
            if (i == 16 || i == 24) { mbar_wait(bar_cnt + i - 16, 0); fence_async(); }
            if (i == RES0) mbar_wait(bar_res, 0);
            if (i == 2) mbar_wait(bar_ofree + (ps - 1) * 16, 0);
            if (elect_one()) {
              if (i == 31) bulk_load(xd, xs, UNIT, bf); else if (!xfirst) bulk_load_stream(xd, xs, UNIT, bf);
              mbar_arrive_pred(bar_go, i == GOST - 1);
              if (PG0 < 16) mbar_arrive_pred(bar_go2, ps == 1 && i == PG0);
              mbar_arrive_pred(bar_od, i == (ps == 1 ? ODS1 : ODS));
              if (i == RES0) mbar_expect_tx(bar_xres, 32768);
              if (i == RES0 || i == RES1) tma2d(base + OFF_RES + (i == RES1) * UNIT, &maps.x, cj * 128 + (i == RES1) * 64, rb * 128, bar_xres);
            }
          }
        }
        if (ps == 2) break;
        wch = ps ? ((wch >> 3) ^ rank) * 2 : wch + 4;
#pragma unroll 1
        for (int u = 0; u < 16; u++) {
          const bool isk = (u == 0) || ((u & 1) && u < 15);
          const int blk = (isk ? (u + 1) >> 1 : (u == 15 ? 7 : (u >> 1) - 1)) & 3;
          const uint32_t sl = base + unit_of(ps ? AT1 : AT0, u & 3) + rank * UNIT, bf = bfull + (u & 3) * 8;
          if (u < 4) mbar_wait(gempty + ((u + 1) >> 1) * 8, 1);
          mbar_wait(bempty + (u & 3) * 8, ((u >> 2) & 1) ^ 1);
          if (elect_one()) {
            mbar_arrive_pred(bar_go2, ps && u + 16 == PG0);
            mbar_expect_tx(bf, SLOT_BYTES);
            tma3d_mc<false>(sl, isk ? &maps.k : &maps.v, 0, kvrow + blk * 128, rank, bf);
          }
        }
      }
      if (elect_one()) mbar_expect_tx(bar_rx, UNIT);
      mbar_wait(bar_rel, 0);
      if (elect_one()) {
        bulk_load_stream(base + UNIT, g_act + (uint32_t)(rb * 80 + 16 + 63 - (cj & 1) * 32) * UNIT, UNIT, bar_rx);
      }
      if (b < NFFN) {
#pragma unroll 1
        for (int u = 0; u < 12; u++) {
          const uint32_t dst = base + unit_of(u < 4 ? FT_G : (u < 8 ? FT_U : FT_D), u & 3);
          if (elect_one()) mbar_expect_tx(bar_box + u * 8, UNIT);
          if (u == FB0 || u == 2 || u == FB2) mbar_wait(bar_ring + (u == FB2 ? 16 : (u + 6) & 8), 0);
          if (u >= FPACE) mbar_wait(bar_box + (u - FPACE) * 8, 0);
          if (elect_one()) {
            if (u < 8) tma2d(dst, u < 4 ? &maps.wg : &maps.wu, b * 32, (u & 3) * 256, bar_box + u * 8);
            else tma3d(dst, &maps.wd, 0, b * 32, (u - 8) * 4, bar_box + u * 8);
          }
        }
      }
    } else if (warp == 9) {
      const uint32_t target = 8 * (epoch + 1);
      uint32_t hmask = 0;
#pragma unroll 1
      for (int i = 0; i < 16; i++) {
        if (i == HDX) mbar_wait(bar_mod, 0);
        const uint32_t need = i == 15 ? 0xffffu : 1u << ((2 * cj + i) & 15);
        if (i >= NRS && (hmask & need) != need) {
          uint32_t n = 0;
          do { hmask = __ballot_sync(0xffffffffu, ld_acquire(&g_cnt_h[rb * 32 + (lane & 15)]) == epoch + 1); watchdog(n); } while ((hmask & need) != need);
          PROF(1, lane == 0 && i == NRS, 26);
          fence_async();
        }
        mbar_wait(xempty + (i & 3) * 8, ((i >> 2) & 1) ^ 1);
        if (elect_one()) {
          mbar_expect_tx(xfull + (i & 3) * 8, UNIT);
          if (i < NRS) tma2d(base + (i & 3) * GST_BYTES, &maps.x, ((2 * cj + i) & 15) * 64, rb * 128, xfull + (i & 3) * 8);
          else bulk_load_stream(base + (i & 3) * GST_BYTES, g_act + (uint32_t)(rb * 80 + ((2 * cj + i) & 15)) * UNIT, UNIT, xfull + (i & 3) * 8);
        }
      }
      prefetch_map(&maps.wo);
#pragma unroll 1
      for (int t = 0; t < 4; t++) {
        if (t & 1) mbar_wait(bar_od, t >> 1);
#pragma unroll 1
        for (int p = 0; p < 32768 / OPS; p++) {
          const uint32_t w = p / (16384 / OPS), c = (p / (8192 / OPS)) & 1, off = w * 8192 + (p % (8192 / OPS)) * OPS;
          mbar_wait(bar_ofull + (t & 1) * 16 + w * 8, t >> 1);
          if (elect_one()) {
            bulk_store(g_act + (uint32_t)(rb * 80 + 16 + (cj * 4 + t) * 2 + c) * UNIT + off, base + unit_of(QT, 2 * t + c) + off, OPS);
            asm volatile("cp.async.bulk.commit_group;" ::: "memory");
            asm volatile("cp.async.bulk.wait_group.read %0;" ::"n"(OFL) : "memory");
          }
        }
        if (elect_one()) {
          asm volatile("cp.async.bulk.wait_group.read 0;" ::: "memory");
          mbar_arrive(t < 3 ? bar_ofree + t * 8 : bar_res);
          asm volatile("cp.async.bulk.wait_group 0;" ::: "memory");
          fence_async();
          red_release(&g_cnt_o[((rb * 4 + t) * 2 + (cj >> 2)) * 32], 2);
        }
        if (t) {
          wait_counter(&g_cnt_o[(rb * 8 + 2 * t + (cj & 1)) * 32], target);
          if (t & 1) wait_counter(&g_cnt_o[(rb * 8 + (t == 1 ? cj & 1 : 7 - (cj & 1))) * 32], target);
          if (elect_one()) mbar_arrive(t == 1 ? bar_ofree + 24 : bar_cnt + t * 8 - 16);
        }
      }
      PROF(2, lane == 0, 27);
      const uint32_t tag = epoch % 3 + 1;
      const uint32_t* inbox = g_cand + (lane & 15);
      mbar_wait(bar_ring + 16, 0);
      uint32_t c0 = ld_relaxed(inbox), n = 0;
#define CAND_STEP(cv)                                                                                        \
      {                                                                                                      \
        const bool valid = (cv & 3u) == tag, all = __all_sync(0xffffffffu, valid);                           \
        const uint32_t best = __reduce_max_sync(0xffffffffu, valid ? cv : 0u);                               \
        const uint32_t blk = __ffs(__ballot_sync(0xffffffffu, cv == best)) - 1;                              \
        if (best) sts2(par + PAR_CONST + 56, best, (blk << 7 | (~best >> 2 & 127)) | (all ? 0x1800 : 0x800)); \
        if (all) break;                                                                                      \
        cv = ld_relaxed(inbox);                                                                              \
      }
      while (true) { CAND_STEP(c0) watchdog(n); }
    } else {
      const int t2 = tid - 320;
      mbar_wait(bar_hpub + (warp & 1) * 8, 0);
      PROF(1, t2 == 0, 24);
#pragma unroll 1
      for (int c = 0; c < 8; c++) {
        const uint32_t off = (warp & 1) * UNIT + c * 2048 + lane * 16;
        uint8_t* dst = g_act + (uint32_t)(rb * 80 + cj * 2) * UNIT + off;
        const uint4 v0 = lds4(stage + off), v1 = lds4(stage + off + 512), v2 = lds4(stage + off + 1024), v3 = lds4(stage + off + 1536);
        stg4(dst, v0); stg4(dst + 512, v1); stg4(dst + 1024, v2); stg4(dst + 1536, v3);
      }
      __syncwarp();
      PROF(1, t2 == 0, 15);
      if (lane == 0) {
        mbar_arrive(bar_pread);
        red_release(&g_cnt_h[rb * 32 + cj * 2 + (warp & 1)], 1);
        PROF(1, t2 == 0, 25);
        prefetch_map(&maps.wg); prefetch_map(&maps.wu); prefetch_map(&maps.wd); prefetch_map(&maps.out);
      }
      __syncwarp();
      if (b < NFFN) {
        mbar_wait(bar_go2, 0);
        const __nv_bfloat16* pg = ((b & 1) ? P.w_up : P.w_gate) + (b >> 1) * 64 + (size_t)t2 * FF;
        const __nv_bfloat16* pd = P.w_down + (size_t)b * 32768 + t2 * 64;
        PROF(2, t2 == 0, 13);
#pragma unroll 1
        for (int i = 0; i < WN; i += WB) {
          uint32_t v[WB];
#pragma unroll
          for (int u = 0; u < WB; u++) {
            const int k = i + u;
            asm volatile("ld.global.cg.L2::128B.u32 %0, [%1];" : "=r"(v[u]) : "l"(k < 16 ? pg + (size_t)k * 64 * FF : pd + (k - 16) * 4096));
          }
#pragma unroll
          for (int u = 1; u < WB; u++) v[0] ^= v[u];
          sts1(par + PAR_SINK + t2 * 4, v[0]);
        }
        PROF(2, t2 == 0, 14);
      }
      const uint32_t tag = epoch % 3 + 1;
      mbar_wait(bar_go, 0);
      if (warp == 10) {
        const uint32_t* src = g_mod + 2 * DM + cj * 128 + lane * 4;
        const uint2 wr = *reinterpret_cast<const uint2*>(P.w_r + cj * 128 + lane * 4);
        uint4 vga, vsb, vcb, vgb;
        uint32_t n = 0;
        do {
          vga = ld_relaxed4(src); vsb = ld_relaxed4(src + DM); vcb = ld_relaxed4(src + 2 * DM); vgb = ld_relaxed4(src + 3 * DM);
          watchdog(n);
        } while (!__all_sync(0xffffffffu, tag_ok(vga, tag) && tag_ok(vsb, tag) && tag_ok(vcb, tag) && tag_ok(vgb, tag)));
        const float c0 = rbf(1.f + bf_hi(vcb.x)), c1 = rbf(1.f + bf_hi(vcb.y)), c2 = rbf(1.f + bf_hi(vcb.z)), c3 = rbf(1.f + bf_hi(vcb.w));
        const float a0 = c0 * bf_lo(wr.x), a1 = c1 * bf_hi(wr.x), a2 = c2 * bf_lo(wr.y), a3 = c3 * bf_hi(wr.y);
        const uint32_t h0 = pack_bf(a0, a1), h1 = pack_bf(a2, a3);
        const uint32_t t1 = par + PAR_T1 + (lane >> 2) * 64 + (lane & 1) * 32 + (lane & 2) * 2;
        sts1(t1, h0); sts1(t1 + 8, pack_bf(a0 - bf_lo(h0), a1 - bf_hi(h0)));
        sts1(t1 + 16, h1); sts1(t1 + 24, pack_bf(a2 - bf_lo(h1), a3 - bf_hi(h1)));
        sts4(par + PAR_T2 + lane * 32, make_uint4(pack_bf(c0, c1), __byte_perm(vsb.x, vsb.y, 0x7632), __byte_perm(vgb.x, vgb.y, 0x7632), __byte_perm(vga.x, vga.y, 0x7632)));
        sts4(par + PAR_T2 + lane * 32 + 16, make_uint4(pack_bf(c2, c3), __byte_perm(vsb.z, vsb.w, 0x7632), __byte_perm(vgb.z, vgb.w, 0x7632), __byte_perm(vga.z, vga.w, 0x7632)));
      } else {
        const uint4 g = poll4((lane & 2) ? g_mod + 8 - (lane & 1) * 4 : g_mod + 5 * DM + b * 8 + (lane & 1) * 4, tag);
        sts1(par + PAR_CONST + 60, 0);
        if (lane < 2) sts4(par + PAR_CONST + 16 + lane * 16, g);
        else if (lane < 4) sts2(par + PAR_CONST + (lane - 2) * 8, __float_as_uint(untag_sum(g.x, g.y) + untag_sum(g.z, g.w)), epoch);
      }
      __syncwarp();
#pragma unroll 4
      for (int q = 0; q < 32; q++) st_b128(g_xch + ((size_t)b * 8 * 256 + q * 64 + t2) * 4, (epoch & 1) << 16, 0, 0, 0);
      for (int q = 0; q < 2; q++) st_relaxed4(g_stats + ((size_t)cj * SEQ + rb * 128 + q * 64 + t2) * 4, 0, 0, 0, 0);
      if (b < NFFN)
        for (int q = 0; q < 4; q++) st_relaxed4(g_ypart + ((size_t)(q * 32 + (t2 >> 1)) * NFFN + b) * 8 + (t2 & 1) * 4, 0, 0, 0, 0);
      st_relaxed4(g_row + rb * 2 * DM + (t2 >> 5) * DM + cj * 128 + (t2 & 31) * 4, 0, 0, 0, 0);
      __threadfence();
      mbar_arrive(bar_par);
      mbar_wait(bar_gate, 0);
      uint32_t have = 0, n = 0;
      while (true) {
        const uint32_t st = lds1(par + PAR_CONST + 60) >> 7;
        if ((st & 31) != have) {
          const uint32_t* hsrc = g_row + (st & 15) * 2 * DM + t2 * 4;
          uint4 hv[4];
          bool ok = true;
#pragma unroll
          for (int i = 0; i < 4; i++) hv[i] = ld_pairs(hsrc + i * 256);
#pragma unroll
          for (int i = 0; i < 4; i++) {
            sts2(base + ((FT_G >> i * 4) & 15) * UNIT + (warp & 1) * 8192 + 256 + lane * 8, hv[i].x, hv[i].z);
            ok = ok && hv[i].y == tag && hv[i].w == tag;
          }
          have = __all_sync(0xffffffffu, ok) ? st & 31 : 0;
        }
        if ((st ^ have) == 32) break;
        watchdog(n);
      }
      mbar_arrive(bar_sel);
    }
    __syncwarp();
    cluster_arrive();
    {
      const uint32_t tag = epoch % 3 + 1, t3 = tid - 256;
      mbar_wait(bar_win, 0);
      uint2 win = lds2(par + PAR_CONST + 56);
      win.y &= 0x7ff;
      const uint32_t* fsrc = g_row + (win.y >> 7) * 2 * DM + (b >> 1) * 16 + (t3 & 3) * 4 + (b & 1) * 2;
      const uint32_t* ysrc = g_ypart + (size_t)b * NFFN * 8 + min(t3, NFFN - 1) * 4;
      uint2 fh = ld_pair(fsrc), fx = ld_pair(fsrc + DM);
      if (PSL) __nanosleep(PSL);
      uint4 ya = ld_relaxed4(ysrc), yb = ld_relaxed4(ysrc + NFFN * 4);
      const float rwin = __uint_as_float(((int)win.x < 0 ? win.x & 0x7fffffffu : ~win.x) & ~0x1ffu);
      const float rs = rbf(rcp(1.f + __expf(-rbf(rwin))));
      uint32_t n = 0;
      while (__any_sync(0xffffffffu, fh.y != tag || fx.y != tag)) { fh = ld_pair(fsrc); fx = ld_pair(fsrc + DM); watchdog(n); }
      while (!__all_sync(0xffffffffu, tag_ok(ya, tag) && tag_ok(yb, tag))) {
        if (!tag_ok(ya, tag)) ya = ld_relaxed4(ysrc);
        if (!tag_ok(yb, tag)) yb = ld_relaxed4(ysrc + NFFN * 4);
        watchdog(n);
      }
      __syncwarp();
      PROF(8, t3 == 0, 5);
      float y0 = untag_sum(ya.x, yb.x), y1 = untag_sum(ya.y, yb.y), y2 = untag_sum(ya.z, yb.z), y3 = untag_sum(ya.w, yb.w);
      const bool u1 = lane & 2, u2 = lane & 4;
      y0 = (u1 ? y2 : y0) + __shfl_xor_sync(0xffffffffu, u1 ? y0 : y2, 2);
      y1 = (u1 ? y3 : y1) + __shfl_xor_sync(0xffffffffu, u1 ? y1 : y3, 2);
      y0 = (u2 ? y1 : y0) + __shfl_xor_sync(0xffffffffu, u2 ? y0 : y1, 4);
      y0 += __shfl_xor_sync(0xffffffffu, y0, 8);
      if (!(lane & 8)) sts1(par + PAR_RED + 64 + (t3 >> 4) * 32 + ((lane & 1) * 4 + (lane & 2) + ((lane >> 2) & 1)) * 4, __float_as_uint(y0));
      bar_sync(4, 128);
      if (t3 < 4) {
        y0 = 0.f; y1 = 0.f;
#pragma unroll
        for (int w4 = 0; w4 < 7; w4++) {
          const uint2 v = lds2(par + PAR_RED + 64 + w4 * 32 + t3 * 8);
          y0 += __uint_as_float(v.x); y1 += __uint_as_float(v.y);
        }
        const uint2 gv = lds2(par + PAR_CONST + 16 + t3 * 8);
        const uint32_t upd = hmul2(pack_bf(y0, y1), pack_bf(rs, rs));
        *reinterpret_cast<uint32_t*>(P.out + (size_t)win.y * DM + b * 8 + t3 * 2) =
            hadd2(fx.x, hmul2(__byte_perm(gv.x, gv.y, 0x7632), hadd2(fh.x, upd)));
        if (b == 0 && t3 == 0) st_relaxed(&g_epoch, epoch + 1);
      }
      PROF(31, t3 == 0, 36);
    }
    cluster_wait();
  } else {
    const int wg = warp >> 2;

    uint32_t tag;
    {
      uint32_t* const pmod = g_modp + rank * 2 * DM + (b >> 1) * 32 + lane;
      uint32_t* const pln = g_ln1 + (rb * 128 + cj * 16 + warp) * 4;
      const uint32_t cv = ldg_nc1(P.c + rank * 512 + tid * 2);
      const uint32_t epoch = ld_relaxed(&g_epoch);
      if (warp == 0) st_relaxed(pmod, 0);
      if (lane == 0) { st_b128(pln, 0, 0, 0, 0); st_b128(pln + 32, 0, 0, 0, 0); }
      asm volatile("setmaxnreg.inc.sync.aligned.u32 232;");
      sts1(par + tid * 4, pack_bf(silu_f(bf_lo(cv)), silu_f(bf_hi(cv))));
      bar_sync(1, 320);
      tag = epoch % 3 + 1;
#pragma unroll
      for (int part = 0; part < 3; part++) {
        if (part != 1) {
          const uint32_t xa = base + (2 + part / 2) * GST_BYTES + warp * 2048 + lane * 16;
          mbar_wait(bar_hx + part * 4, 0);
          float s0 = 0.f, s1 = 0.f, q0 = 0.f, q1 = 0.f;
#pragma unroll
          for (int q = 0; q < 4; q++) {
            const uint4 xv = lds4(xa + q * 512);
            const uint32_t u[4] = {xv.x, xv.y, xv.z, xv.w};
#pragma unroll
            for (int e = 0; e < 4; e++) { const float lo = bf_lo(u[e]), hi = bf_hi(u[e]); s0 += lo; s1 += hi; q0 += lo * lo; q1 += hi * hi; }
          }
          s0 += s1; q0 += q1;
#pragma unroll
          for (int o = 16; o > 0; o >>= 1) { s0 += __shfl_xor_sync(0xffffffffu, s0, o); q0 += __shfl_xor_sync(0xffffffffu, q0, o); }
          const float mean = s0 * (1.f / DM);
          float mb, sd;
          ln_scalars(mean, fmaxf(q0 * (1.f / DM) - mean * mean, 0.f), mb, sd);
          uint32_t ih, il;
          split_inv(sd, ih, il);
          if (lane == 0) st_b128(pln + part * 16, pack_bf(mb, mb), ih, il, tag);
          PROF(1, tid == 0 && part == 2, 4);
        } else {
          float acc[8];
#pragma unroll
          for (int e = 0; e < 8; e++) acc[e] = 0.f;
          const uint32_t wa = stage + (tid >> 2) * 64 + (((tid ^ (tid >> 3)) & 3) << 4), sa = par + (tid >> 3) * 4, sh = (tid & 4) ? 0x3244 : 0x1044;
          mbar_wait(bar_hw, 0);
#pragma unroll
          for (int p = 0; p < 8; p++) {
            const uint4 w = lds4(wa + p * 4096);
            const float s = __uint_as_float(__byte_perm(lds1(sa + p * 128), 0, sh));
            acc[0] += s * bf_lo(w.x); acc[1] += s * bf_hi(w.x); acc[2] += s * bf_lo(w.y); acc[3] += s * bf_hi(w.y);
            acc[4] += s * bf_lo(w.z); acc[5] += s * bf_hi(w.z); acc[6] += s * bf_lo(w.w); acc[7] += s * bf_hi(w.w);
          }
#pragma unroll
          for (int e = 0; e < 4; e++) {
            const bool up = lane & 16;
            acc[e] = (up ? acc[e + 4] : acc[e]) + __shfl_xor_sync(0xffffffffu, up ? acc[e] : acc[e + 4], 16);
          }
#pragma unroll
          for (int e = 0; e < 2; e++) {
            const bool up = lane & 8;
            acc[e] = (up ? acc[e + 2] : acc[e]) + __shfl_xor_sync(0xffffffffu, up ? acc[e] : acc[e + 2], 8);
          }
          {
            const bool up = lane & 4;
            acc[0] = (up ? acc[1] : acc[0]) + __shfl_xor_sync(0xffffffffu, up ? acc[0] : acc[1], 4);
          }
          sts1(base + 2 * GST_BYTES + warp * 2048 + ((lane & 3) * 8 + (lane >> 2)) * 4, __float_as_uint(acc[0]));
          bar_sync(1, 256);
          if (warp == 0) {
            float s = 0.f;
#pragma unroll
            for (int w8 = 0; w8 < 8; w8++) s += __uint_as_float(lds1(base + 2 * GST_BYTES + w8 * 2048 + lane * 4));
            st_relaxed(pmod, (__float_as_uint(s) & ~3u) | tag);
          }
          PROF(1, tid == 0, 3);
        }
      }
      cluster_wait();
      if (wg == 1) bar_arrive(2, 256);
    }

    float f0 = 0.f, f1 = 0.f;
    const uint32_t rempty = lane < 2 ? mapa(bempty, lane & 1) : 0;
    constexpr uint32_t GE = NSLOT * 8 + 32;
    float o[64], s[64];
#pragma unroll 1
    for (int ps = 0; ps < 3; ps++) {
      {
        const uint32_t xt = ps == 1 ? XT1 : XT2, wt = ps == 1 ? WT1 : WT2;
        const int nst = ps == 2 ? 28 : 14;
        if (ps == 0) {
          float ga[64], gb[64];
#pragma unroll
          for (int i = 0; i < 64; i++) { ga[i] = 0.f; gb[i] = 0.f; }
          uint32_t a[2][16];
          const uint32_t l = fresh_lane();
          uint32_t fa[4];
#pragma unroll
          for (int kk = 0; kk < 4; kk++) fa[kk] = (base + wg * 8192 + frag_offset(warp)) ^ (kk * 32);
          const uint32_t mt = par + (l & 3) * 16;
          auto fetch = [&](int i, uint32_t (&f)[16], uint32_t z) {
            mbar_wait(xfull + (i & 3) * 8, i >> 2);
#pragma unroll
            for (int kk = 0; kk < 4; kk++) ldmatrix4(fa[kk] + (i & 3) * GST_BYTES + z, f[4 * kk], f[4 * kk + 1], f[4 * kk + 2], f[4 * kk + 3]);
          };
          uint4 r0, r1;
          {
            const uint32_t t7 = (warp & 3) * 32 + l;
            const uint32_t* pm = g_modp + wg * DM + ((cj * 128 + t7 * 4) & (DM - 1));
            const uint32_t* pr = g_ln1 + (rb * 128 + warp * 16 + (l >> 2)) * 4;
            uint4 m0 = ld_relaxed4(pm), m1 = ld_relaxed4(pm + 2 * DM);
            r0 = ld_b128(pr); r1 = ld_b128(pr + 32);
            fetch(0, a[0], 0); fetch(1, a[1], 0);
            uint32_t n = 0;
            bool written = false;
#pragma unroll 1
            while (true) {
              uint32_t miss;
              asm volatile("{ .reg .pred p0, p1, p2, p3; .reg .b32 t, u;\n"
                           "lop3.b32 t, %1, %2, %19, 0x7e; lop3.b32 u, %3, %4, %19, 0x7e; or.b32 t, t, u; and.b32 t, t, 3; setp.ne.u32 p0, t, 0;\n"
                           "lop3.b32 t, %5, %6, %19, 0x7e; lop3.b32 u, %7, %8, %19, 0x7e; or.b32 t, t, u; and.b32 t, t, 3; setp.ne.u32 p1, t, 0;\n"
                           "setp.ne.u32 p2, %12, %19; setp.ne.u32 p3, %16, %19;\n"
                           "@p0 ld.relaxed.gpu.global.v4.u32 {%1, %2, %3, %4}, [%17];\n"
                           "@p1 ld.relaxed.gpu.global.v4.u32 {%5, %6, %7, %8}, [%17 + 8192];\n"
                           "@p2 ld.relaxed.gpu.global.v4.u32 {%9, %10, %11, %12}, [%18];\n"
                           "@p3 ld.relaxed.gpu.global.v4.u32 {%13, %14, %15, %16}, [%18 + 128];\n"
                           "or.pred p0, p0, p1; or.pred p2, p2, p3; vote.sync.any.pred p0, p0, 0xffffffff; vote.sync.any.pred p2, p2, 0xffffffff;\n"
                           "selp.u32 t, 1, 0, p0; selp.u32 u, 2, 0, p2; or.b32 %0, t, u; }"
                           : "=r"(miss), "+r"(m0.x), "+r"(m0.y), "+r"(m0.z), "+r"(m0.w), "+r"(m1.x), "+r"(m1.y), "+r"(m1.z), "+r"(m1.w),
                             "+r"(r0.x), "+r"(r0.y), "+r"(r0.z), "+r"(r0.w), "+r"(r1.x), "+r"(r1.y), "+r"(r1.z), "+r"(r1.w)
                           : "l"(pm), "l"(pr), "r"(tag) : "memory");
              if (!(miss & 1) && !written) {
                written = true;
                float c0 = untag_sum(m0.x, m1.x), c1 = untag_sum(m0.y, m1.y), c2 = untag_sum(m0.z, m1.z), c3 = untag_sum(m0.w, m1.w);
                if (wg) { c0 = 1.f + rbf(c0); c1 = 1.f + rbf(c1); c2 = 1.f + rbf(c2); c3 = 1.f + rbf(c3); }
                const uint32_t d = par + (t7 >> 2) * 64 + (t7 & 1) * 32 + (t7 & 2) * 2 + (wg ? 0 : 8);
                sts1(d, pack_bf(c0, c1));
                sts1(d + 16, pack_bf(c2, c3));
                mbar_arrive(bar_mod);
              }
              if (!miss) break;
              watchdog(n);
            }
          }
          const uint32_t zero = r0.w ^ tag;
          auto normalize = [&](uint32_t (&f)[16]) {
#pragma unroll
            for (int k = 0; k < 16; k += 2) { f[k] = ln_norm(f[k], r0.x, r0.y, r0.z); f[k + 1] = ln_norm(f[k + 1], r1.x, r1.y, r1.z); }
          };
          auto modulate = [&](int i, uint32_t (&f)[16]) {
#pragma unroll
            for (int kk = 0; kk < 4; kk++) {
              const uint4 m = lds4(mt + i * 256 + kk * 64);
              f[4 * kk] = MODUL(f[4 * kk], m.x, m.z); f[4 * kk + 1] = MODUL(f[4 * kk + 1], m.x, m.z);
              f[4 * kk + 2] = MODUL(f[4 * kk + 2], m.y, m.w); f[4 * kk + 3] = MODUL(f[4 * kk + 3], m.y, m.w);
            }
            keep(f);
            mbar_arrive_pred(xempty + (i & 3) * 8, l == 0);
          };
          auto publish = [&](int u, uint32_t (&f)[16]) {
#pragma unroll
            for (int kk = 0; kk < 4; kk++) stmatrix4(fa[kk] + OFF_STAGE + u * UNIT, f[4 * kk], f[4 * kk + 1], f[4 * kk + 2], f[4 * kk + 3]);
            __syncwarp();
            mbar_arrive_pred(bar_hpub + u * 8, l == 0);
          };
          auto multiply = [&](int i, uint32_t (&f)[16]) {
            mbar_wait(gfull + (i & 3) * 8, i >> 2);
            const uint64_t db = make_desc(base + (i & 3) * GST_BYTES + UNIT, 8192, 1024);
            wg_fence();
#pragma unroll
            for (int kk = 0; kk < 4; kk++) mma256_rs(ga, gb, f[4 * kk], f[4 * kk + 1], f[4 * kk + 2], f[4 * kk + 3], db + kk * 128);
            wg_commit();
          };
          auto next = [&](int i, uint32_t (&f)[16]) {
            wg_wait<1>();
            mbar_arrive_cl(rempty, GE + ((i + 2) & 3) * 8);
            uint32_t z = zero;
#pragma unroll
            for (int k = 0; k < 16; k += 2) asm volatile("lop3.b32 %0, %1, %2, %0, 0xA8;" : "+r"(z) : "r"(f[k]), "r"(f[k + 1]));
            fetch(i, f, z);
            normalize(f); modulate(i, f); multiply(i, f);
          };
          normalize(a[0]); normalize(a[1]);
          keep(a[0]); keep(a[1]);
          mbar_wait(bar_mod, 0);
          PROF(1, tid == 0, 2);
          modulate(0, a[0]); multiply(0, a[0]); publish(0, a[0]);
          modulate(1, a[1]); multiply(1, a[1]); publish(1, a[1]);
#pragma unroll 1
          for (int i = 2; i < NRS; i += 2) { next(i, a[0]); next(i + 1, a[1]); }
          wg_wait<1>();
          mbar_arrive_cl(rempty, GE + ((NRS + 2) & 3) * 8);
#pragma unroll 1
          for (int i = NRS; i < 14; i++) {
            mbar_wait(xfull + (i & 3) * 8, (i >> 2) & 1);
            mbar_wait(gfull + (i & 3) * 8, (i >> 2) & 1);
            const uint32_t xa = base + (i & 3) * GST_BYTES;
            const uint64_t da = make_desc(xa + wg * 8192, 16, 1024), db = make_desc(xa + UNIT, 8192, 1024);
            if (i == 13) bar_sync(2 + wg, 256);
            wg_fence();
#pragma unroll
            for (int kk = 0; kk < 4; kk++) mma256_ss(ga, gb, da + kk * 2, db + kk * 128, 1);
            wg_commit();
            if (i == 13) bar_arrive(3 - wg, 256);
            wg_wait<1>();
            uint32_t z = zero;
#pragma unroll
            for (int k = 0; k < 16; k += 2) asm volatile("lop3.b32 %0, %1, %2, %0, 0xA8;" : "+r"(z) : "r"(a[1][k]), "r"(a[1][k + 1]));
            mbar_arrive_cl(rempty, GE + ((i + 3) & 3) * 8 + z);
            mbar_arrive_pred(xempty + ((i + 3) & 3) * 8, l == 0 && i != NRS);
          }
          mbar_wait(xfull + 16, 1);
          wg_wait<0>();
          keep(ga); keep(gb);
#pragma unroll
          for (int i = 0; i < 64; i++) {
            asm volatile("mov.b32 %0, %1;" : "=f"(s[i]) : "f"(ga[i]));
            asm volatile("mov.b32 %0, %1;" : "=f"(o[i]) : "f"(gb[i]));
          }
        } else {
          float ga[64], gb[64];
#pragma unroll
          for (int i = 0; i < 64; i++) {
            asm volatile("mov.b32 %0, %1;" : "=f"(ga[i]) : "f"(s[i]));
            asm volatile("mov.b32 %0, %1;" : "=f"(gb[i]) : "f"(o[i]));
          }
#pragma unroll 1
          for (int i = 0; i < nst; i++) {
            mbar_wait(gfull + (i & 3) * 8, (i >> 2) & 1);
            const uint64_t da = make_desc(base + unit_of(xt, i & 3) + wg * 8192, 16, 1024), db = make_desc(base + unit_of(wt, i & 3), 8192, 1024);
            if (i == nst - 1) bar_sync(2 + wg, 256);
            wg_fence();
#pragma unroll
            for (int kk = 0; kk < 4; kk++) mma256_ss(ga, gb, da + kk * 2, db + kk * 128, kk ? 1 : i);
            wg_commit();
            if (i == nst - 1) bar_arrive(3 - wg, 256);
            wg_wait<1>();
            mbar_arrive_cl(rempty, GE + ((i + 3) & 3) * 8, i != 0);
            PROF(4, tid == 0 && (i & 3) == 0, 40 + (ps - 1) * 4 + i / 4);
          }
          wg_wait<0>();
          keep(ga); keep(gb);
#pragma unroll
          for (int i = 0; i < 64; i++) {
            asm volatile("mov.b32 %0, %1;" : "=f"(s[i]) : "f"(ga[i]));
            asm volatile("mov.b32 %0, %1;" : "=f"(o[i]) : "f"(gb[i]));
          }
        }
        mbar_arrive_cl(rempty, GE + (ps == 2 ? 24 : 8));
        if (ps == 2) break;
      }
      const uint32_t qw = base + wg * 8192, qt = QT >> (16 * ps), at = ps ? AT1 : AT0;
      {
        const uint32_t wt = ps ? WT1 : WT0;
        const uint64_t da0 = make_desc(qw + unit_of(qt, 2), 16, 1024), da1 = make_desc(qw + unit_of(qt, 3), 16, 1024);
        const uint64_t db0 = make_desc(base + unit_of(wt, 2), 8192, 1024), db1 = make_desc(base + unit_of(wt, 3), 8192, 1024);
        mbar_wait(gfull + 16, 1);
        bar_sync(2 + wg, 256);
        wg_fence();
#pragma unroll
        for (int kk = 0; kk < 4; kk++) mma_ss<1>(s, da0 + kk * 2, db0 + kk * 128, 1);
        wg_commit();
        mbar_wait(xfull + 24, 1);
        mbar_wait(gfull + 24, 1);
        wg_fence();
#pragma unroll
        for (int kk = 0; kk < 4; kk++) mma_ss<1>(s, da1 + kk * 2, db1 + kk * 128, 1);
        wg_commit();
        bar_arrive(3 - wg, 256);
        mbar_wait(ps == 0 ? bar_pread : bar_ofree + 8, 0);
        wg_wait<0>();
        keep(s);
        PROF(2, tid == 0, 8 + ps * 8);
        store_chunk<0>(s, qw + unit_of(qt, 0) + frag_offset(warp));
        store_chunk<1>(s, qw + unit_of(qt, 1) + frag_offset(warp));
        fence_async_smem();
        bar_sync(2 + wg, 256);
        wg_fence();
#pragma unroll
        for (int kk = 0; kk < 8; kk++) mma_ss<1>(o, (kk < 4 ? da0 : da1) + (kk & 3) * 2, (kk < 4 ? db0 : db1) + UNIT / 16 + (kk & 3) * 128, 1);
        wg_commit();
        mbar_wait(bfull, 0);
        wg_fence();
        issue_qk(s, qw + unit_of(qt, 0), qw + unit_of(qt, 1), base + unit_of(at, 0));
        wg_commit();
        bar_arrive(3 - wg, 256);
        wg_wait<1>();
        keep(o);
        mbar_arrive_cl(rempty, GE + 16);
        mbar_arrive_cl(rempty, GE + 24);
        store_chunk<0>(o, qw + unit_of(qt, 2) + frag_offset(warp));
        store_chunk<1>(o, qw + unit_of(qt, 3) + frag_offset(warp));
        wg_wait<0>();
        keep(s);
        mbar_arrive_cl(rempty, 0);
      }
      PROF(4, tid == 0 && ps == 1, 61);
      float l0 = 0.f, l1 = 0.f;
      auto step = [&](auto odd_c, const int j, uint32_t (&pw)[32], uint32_t (&pr)[32]) {
        constexpr bool ODD = decltype(odd_c)::value;
        const bool first = !ODD && (j & 2) == 0, last = ODD && j == 7;
        const uint32_t ph = (j >> 1) & 1;
        float i0, i1, a0, a1;
        const bool so = !ODD && j == 4;
        if (so) { i0 = inv_quad_sum(l0); i1 = inv_quad_sum(l1); l0 = 0.f; l1 = 0.f; }
        bool redo = !ODD && (j | ps) == 0;
        while (true) {
          if (redo) {
            float m0 = fmaxf(s[0], s[1]), m1 = fmaxf(s[2], s[3]);
#pragma unroll
            for (int i = 1; i < 16; i++) { m0 = fmaxf(m0, fmaxf(s[4 * i], s[4 * i + 1])); m1 = fmaxf(m1, fmaxf(s[4 * i + 2], s[4 * i + 3])); }
            m0 = fmaxf(m0, __shfl_xor_sync(0xffffffffu, m0, 1)); m1 = fmaxf(m1, __shfl_xor_sync(0xffffffffu, m1, 1));
            m0 = fmaxf(m0, __shfl_xor_sync(0xffffffffu, m0, 2)); m1 = fmaxf(m1, __shfl_xor_sync(0xffffffffu, m1, 2));
            m0 *= SCL2; m1 *= SCL2;
            if (!first) {
              m0 = fmaxf(m0, f0); m1 = fmaxf(m1, f1);
              const float c0 = ex2(f0 - m0), c1 = ex2(f1 - m1);
              l0 *= c0; l1 *= c1;
              wg_wait<0>();
              keep(o);
#pragma unroll
              for (int i = 0; i < 16; i++) { o[4 * i] *= c0; o[4 * i + 1] *= c0; o[4 * i + 2] *= c1; o[4 * i + 3] *= c1; }
            }
            f0 = m0; f1 = m1;
          }
          float b0 = 0.f, b1 = 0.f, g0 = f0, g1 = f1, h0 = f0, h1 = f1;
          a0 = 0.f; a1 = 0.f;
#pragma unroll
          for (int i = 0; i < 16; i++) {
            if (SG && i % SG == 0 && i) {
              g0 = h0; g1 = h1;
              asm("fma.rn.f32 %0, %1, 0f00000000, %2;" : "=f"(h0) : "f"(SGB ? b0 : a0), "f"(f0));
              asm("fma.rn.f32 %0, %1, 0f00000000, %2;" : "=f"(h1) : "f"(SGB ? b1 : a1), "f"(f1));
            }
            const float e0 = ex2(fmaf(s[4 * i], SCL2, -g0)), e1 = ex2(fmaf(s[4 * i + 1], SCL2, -g0));
            const float e2 = ex2(fmaf(s[4 * i + 2], SCL2, -g1)), e3 = ex2(fmaf(s[4 * i + 3], SCL2, -g1));
            if (SGB) { a0 += e0; b0 += e1; a1 += e2; b1 += e3; } else { a0 = (a0 + e0) + e1; a1 = (a1 + e2) + e3; }
            pw[2 * i] = pack_bf(e0, e1); pw[2 * i + 1] = pack_bf(e2, e3);
            if (i == VREL) {
#pragma unroll
              for (int k = 0; k < 2 * VREL + 2; k++) asm volatile("" : "+r"(pw[k])::"memory");
              mbar_wait(bar_mod, 0);
              wg_wait<0>();
              mbar_arrive_cl(rempty, ODD ? 16 : 0, !redo && (ODD || j));
#pragma unroll
              for (int k = 4 * VREL + 4; k < 64; k++) asm volatile("" : "+f"(s[k])::"memory");
            }
          }
          if (SGB) { a0 += b0; a1 += b1; }
          if (redo) break;
          redo = __any_sync(0xffffffffu, !(a0 + a1 < 0x1p70f));
          if (first) {
            uint32_t m0 = __ballot_sync(0xffffffffu, a0 > 0x1p-50f), m1 = __ballot_sync(0xffffffffu, a1 > 0x1p-50f);
            m0 |= m0 >> 1; m1 |= m1 >> 1; m0 |= m0 >> 2; m1 |= m1 >> 2;
            redo = redo || (m0 & m1 & 0x11111111u) != 0x11111111u;
          }
          if (!redo) break;
        }
        l0 += a0; l1 += a1;
        keep(pw);
        keep(o);
        if (so) store_chunk<0>(o, i0, i1, qw + unit_of(qt, 0) + frag_offset(warp));
        keep(o);
        if (ODD && !(j & 2)) { fence_async_smem(); mbar_arrive_pred(bar_ofull + wg * 8, j > 4); }
        mbar_wait(bfull + (ODD ? 24 : 8), ph);
        bar_sync(2 + wg, 256);
        if (!last) {
          const uint32_t qn = qt >> (j >= 3 ? 8 : 0);
          wg_fence();
          issue_qk(s, qw + unit_of(qn, 0), qw + unit_of(qn, 1), base + unit_of(at, ODD ? 3 : 1));
          wg_commit();
          mbar_wait(bfull + (ODD ? 0 : 16), ODD ? ph ^ 1 : ph);
        }
        if (so) { store_chunk<1>(o, i0, i1, qw + unit_of(qt, 1) + frag_offset(warp)); keep(o); }
        wg_fence();
        issue_pv(o, pw, base + unit_of(at, ODD ? (last ? 3 : 0) : 2), !first);
        wg_commit();
        bar_arrive(3 - wg, 256);
        wg_wait<1>();
        keep(s);
        mbar_arrive_cl(rempty, ODD ? 24 : 8, !last);
        PROF(4, tid == 0 && ps == 1, 51 + j);
      };
      uint32_t pa[32], pb[32];
#pragma unroll 1
      for (int j = 0; j < 8; j += 2) {
        step(std::false_type{}, j, pa, pb);
        step(std::true_type{}, j + 1, pb, pa);
      }
      {
        const float i0 = inv_quad_sum(l0), i1 = inv_quad_sum(l1);
        wg_wait<0>();
        keep(o);
        mbar_arrive_cl(rempty, 24);
        store_chunk<0>(o, i0, i1, qw + unit_of(qt, 2) + frag_offset(warp));
        store_chunk<1>(o, i0, i1, qw + unit_of(qt, 3) + frag_offset(warp));
        fence_async_smem();
        mbar_arrive(bar_ofull + 16 + wg * 8);
      }
      PROF(2, tid == 0, 10 + ps * 8);
    }

    const int ln = fresh_lane(), g = ln >> 2, tq = ln & 3, ct = warp * 32 + ln;
    const bool lane0 = ln == 0;
    const int lrow0 = warp * 16 + g;
    const int grow0 = rb * 128 + lrow0;
    const uint32_t res = base + OFF_RES, trow = res + wg * 8192 + frag_offset(warp);
    uint32_t xr[32];
    uint4 sv[4], own;
    uint32_t* sp[4];
#pragma unroll
    for (int k = 0; k < 4; k++) sp[k] = g_stats + ((((tq >> 1) * 4 + k) ^ cj) * SEQ + grow0 + (tq & 1) * 8) * 4;
    {
      const uint64_t da = make_desc(base + wg * 8192, 16, 1024), db = make_desc(base, 8192, 1024);
      constexpr int U = UNIT / 16;
#define HALF_STAGE(acc, xu, wu) _Pragma("unroll") for (int kk = 0; kk < 4; kk++) mma_ss<1>(acc, da + (xu) * U + kk * 2, db + (wu) * U + kk * 128, 1)
      PROF(10, ct == PT, 19); STAMP(0);
      cluster_arrive();
      mbar_wait(gfull, 1);
      mbar_wait(gfull + 8, 1);
      bar_sync(2 + wg, 256);
      wg_fence();
      HALF_STAGE(o, 7, 1);
      HALF_STAGE(o, 8, 3);
      wg_commit();
      STAMP(16);
      mbar_wait(gfull + 16, 1);
      STAMP(17);
      wg_fence();
      HALF_STAGE(o, 6, 11);
      wg_commit();
      bar_arrive(3 - wg, 256);
      mbar_wait(bar_par, 0);
      uint32_t* xo = g_xch + ((size_t)b * 8 * 256 + ct) * 4;
      const uint32_t* xi = g_xch + ((size_t)(b ^ 2) * 8 * 256 + ct) * 4;
      const uint32_t par1 = (~lds1(par + PAR_CONST + 4) & 1) << 16;
      uint32_t ga[16];
      uint4 bw[8];
#define LOAD_PAR _Pragma("unroll") for (int i = 0; i < 8; i++) {                                                               \
        ga[2 * i] = lds1(par + PAR_T2 + i * 128 + tq * 16 + 12); ga[2 * i + 1] = lds1(par + PAR_T2 + i * 128 + 64 + tq * 16 + 12); \
        bw[i] = lds4(par + PAR_T1 + i * 64 + tq * 16);                                                                          \
        if (!(g & 1)) { bw[i].x = 0x3f803f80u; bw[i].y = 0x3f803f80u; }                                                         \
      }
      if (PPOS == 0) LOAD_PAR
      wg_wait<1>();
      mbar_arrive_pred(bar_rel, lane0);
      wg_wait<0>();
      keep(o);
      mbar_arrive_pred(bar_ring, lane0);
      PROF(8, ct == PT, 20); STAMP(1);
#define SEND(i) st_b128(xo + (i) * 1024, (pack_bf(o[8 * (i)], o[8 * (i) + 1]) & ~0x10000u) | par1, pack_bf(o[8 * (i) + 2], o[8 * (i) + 3]), \
                        pack_bf(o[8 * (i) + 4], o[8 * (i) + 5]), pack_bf(o[8 * (i) + 6], o[8 * (i) + 7]))
#pragma unroll
      for (int i = 0; i < NS1; i++) SEND(i);
      PROF(8, ct == PT, 21); STAMP(2);
      bar_sync(2 + wg, 256);
      wg_fence();
      HALF_STAGE(s, 7, 0);
      HALF_STAGE(s, 8, 2);
      HALF_STAGE(s, 6, 10);
      wg_commit();
      bar_arrive(3 - wg, 256);
      STAMP(18);
      mbar_wait(gfull + 24, 1);
#pragma unroll
      for (int i = NS1; i < 8; i++) SEND(i);
      uint4 v[8];
#pragma unroll
      for (int i = 0; i < 4; i++) v[i] = ld_b128(xi + i * 1024);
      if (PPOS == 1) LOAD_PAR
      STAMP(19);
      mbar_wait(bar_xres, 0);
      wg_wait<0>();
      mbar_arrive_pred(bar_ring + 8, lane0);
      bar_sync(2 + wg, 256);
      STAMP(20);
#pragma unroll
      for (int i = 4; i < 8; i++) v[i] = ld_b128(xi + i * 1024);
      mbar_wait(bar_xres, 0);
      wg_fence();
      HALF_STAGE(s, 9, 4);
      wg_commit();
      mbar_wait(bar_rx, 0);
      wg_fence();
      HALF_STAGE(s, 1, 5);
      wg_commit();
      bar_arrive(3 - wg, 256);
      STAMP(21);
      wg_wait<0>();
      keep(s);
      mbar_arrive_pred(bar_ring + 16, lane0);
      PROF(10, ct == PT, 23); STAMP(4);
#pragma unroll
      for (int i = 0; i < 16; i += 2) ldmatrix4((trow ^ ((i & 7) << 4)) + (i >> 3) * 16384, xr[2 * i], xr[2 * i + 1], xr[2 * i + 2], xr[2 * i + 3]);
      if (PPOS == 2) LOAD_PAR
      uint32_t pk[32];
      pack_p(s, pk);
      keep(pk);
      {
        uint32_t n = 0, miss;
        do {
          miss = 0;
#pragma unroll
          for (int i = 0; i < 8; i++) miss |= v[i].x ^ par1;
          miss = __any_sync(0xffffffffu, miss & 0x10000u);
          if (miss) {
#pragma unroll
            for (int i = 0; i < 8; i++)
              asm volatile("{ .reg .pred p; .reg .b32 t; xor.b32 t, %0, %5; and.b32 t, t, 0x10000; setp.ne.u32 p, t, 0;\n"
                           "@p ld.relaxed.gpu.global.v4.u32 {%0, %1, %2, %3}, [%4]; }"
                           : "+r"(v[i].x), "+r"(v[i].y), "+r"(v[i].z), "+r"(v[i].w) : "l"(xi + i * 1024), "r"(par1) : "memory");
          }
          watchdog(n);
        } while (miss);
      }
      PROF(8, ct == PT, 22); STAMP(3);
#pragma unroll
      for (int k = 0; k < 4; k++) sv[k] = ESV ? ld_b128(sp[k]) : make_uint4(0, 0, 0, 0);
      float ds[4] = {0.f, 0.f, 0.f, 0.f}, dl[4] = {0.f, 0.f, 0.f, 0.f}, q0[4] = {0.f, 0.f, 0.f, 0.f}, q1[4] = {0.f, 0.f, 0.f, 0.f};
#pragma unroll
      for (int i = 0; i < 8; i++) {
        const uint32_t u0 = hfma2(ga[2 * i], hadd2(pk[4 * i], v[i].x & ~0x10000u), xr[4 * i]);
        const uint32_t u1 = hfma2(ga[2 * i], hadd2(pk[4 * i + 1], v[i].y), xr[4 * i + 1]);
        const uint32_t u2 = hfma2(ga[2 * i + 1], hadd2(pk[4 * i + 2], v[i].z), xr[4 * i + 2]);
        const uint32_t u3 = hfma2(ga[2 * i + 1], hadd2(pk[4 * i + 3], v[i].w), xr[4 * i + 3]);
        xr[4 * i] = u0; xr[4 * i + 1] = u1; xr[4 * i + 2] = u2; xr[4 * i + 3] = u3;
        mma16816(ds, u0, u1, u2, u3, bw[i].x, bw[i].y);
        mma16816(dl, u0, u1, u2, u3, bw[i].z, bw[i].w);
        mma16816(q0, u0, u1, u2, u3, u0, u2);
        mma16816(q1, u0, u1, u2, u3, u1, u3);
      }
      const float sqa = __shfl_sync(0xffffffffu, (g & 1) ? q0[1] : q0[0], g * 4 + (g >> 1));
      const float sqb = __shfl_sync(0xffffffffu, (g & 1) ? q1[3] : q1[2], g * 4 + (g >> 1));
      own = (tq & 1) ? make_uint4(__float_as_uint(ds[2]), __float_as_uint(sqb), __float_as_uint(ds[3] + dl[3]), tag)
                                 : make_uint4(__float_as_uint(ds[0]), __float_as_uint(sqa), __float_as_uint(ds[1] + dl[1]), tag);
      if (tq < 2) st_b128(sp[0], own.x, own.y, own.z, own.w);
    }
    PROF(8, ct == PT, 29); STAMP(5);
    uint32_t mm, ih, il;
    float rbest;
    uint32_t wf[128];
    const uint32_t frow = (ln & 7) + (ln >> 4) * 8;
    const uint32_t wfo = base + (warp & 1) * 8192 + frow * 64 + ((((ln >> 3) & 1) ^ ((frow >> 1) & 3)) << 4);
#define LOAD_WF(m) _Pragma("unroll") for (int f = 0; f < 16; f++) {                                                   \
      const int r = ((f >> 1) * 4 + (m) * 2 + (f & 1)) * 4;                                                           \
      ldmatrix4t(((wfo + unit_of((m) ? FT_U : FT_G, warp >> 1)) ^ ((f & 1) * 32)) + (f >> 1) * 1024, wf[r], wf[r + 1], wf[r + 2], wf[r + 3]); \
    }
    bool early, wait1;
    {
#pragma unroll
      for (int i = 0; i < 16; i += 2) stmatrix4((trow ^ ((i & 7) << 4)) + (i >> 3) * 16384, xr[2 * i], xr[2 * i + 1], xr[2 * i + 2], xr[2 * i + 3]);
      const uint4 cst = lds4(par + PAR_CONST);
      const float A1 = __uint_as_float(cst.x), A2 = __uint_as_float(cst.z);
      uint32_t n = 0;
      early = false; wait1 = false;
#pragma unroll 1
      while (true) {
        uint32_t miss;
        asm volatile("{ .reg .pred p0, p1, p2, p3; .reg .b64 u, v; .reg .b128 w;\n"
                     "setp.ge.u32 p0, %22, 2; setp.ne.and.u32 p0, %4, %21, p0; setp.ne.u32 p1, %8, %21; setp.ne.u32 p2, %12, %21; setp.ne.u32 p3, %16, %21;\n"
                     "@p0 ld.relaxed.gpu.global.v4.u32 {%1, %2, %3, %4}, [%17];\n"
                     "@p1 ld.relaxed.gpu.global.v4.u32 {%5, %6, %7, %8}, [%18];\n"
                     "@p2 ld.relaxed.gpu.global.v4.u32 {%9, %10, %11, %12}, [%19];\n"
                     "@p3 ld.relaxed.gpu.global.v4.u32 {%13, %14, %15, %16}, [%20];\n"
                     "or.pred p0, p0, p1; or.pred p2, p2, p3; or.pred p0, p0, p2; vote.sync.any.pred p0, p0, 0xffffffff; selp.u32 %0, 1, 0, p0; }"
                     : "=r"(miss), "+r"(sv[0].x), "+r"(sv[0].y), "+r"(sv[0].z), "+r"(sv[0].w), "+r"(sv[1].x), "+r"(sv[1].y), "+r"(sv[1].z), "+r"(sv[1].w),
                       "+r"(sv[2].x), "+r"(sv[2].y), "+r"(sv[2].z), "+r"(sv[2].w), "+r"(sv[3].x), "+r"(sv[3].y), "+r"(sv[3].z), "+r"(sv[3].w)
                     : "l"(sp[0]), "l"(sp[1]), "l"(sp[2]), "l"(sp[3]), "r"(tag), "r"(tq) : "memory");
        if (!miss) break;
        wait1 = true;
        if (!early && (b >= NFFN || __all_sync(0xffffffffu, mbar_test(bar_box + (warp >> 1) * 8, 0)))) {
          early = true;
          LOAD_WF(0);
          __syncwarp();
          mbar_arrive_pred(bar_gate, lane0);
        }
        watchdog(n);
      }
      const uint4 v0 = tq < 2 ? own : sv[0], v1 = sv[1], v2 = sv[2], v3 = sv[3];
      PROF(8, ct == PT, 30); STAMP(6);
      float su = (__uint_as_float(v0.x) + __uint_as_float(v1.x)) + (__uint_as_float(v2.x) + __uint_as_float(v3.x));
      float sq = (__uint_as_float(v0.y) + __uint_as_float(v1.y)) + (__uint_as_float(v2.y) + __uint_as_float(v3.y));
      float dt = (__uint_as_float(v0.z) + __uint_as_float(v1.z)) + (__uint_as_float(v2.z) + __uint_as_float(v3.z));
      su += __shfl_xor_sync(0xffffffffu, su, 2); sq += __shfl_xor_sync(0xffffffffu, sq, 2); dt += __shfl_xor_sync(0xffffffffu, dt, 2);
      const float m = su * (1.f / DM);
      float mb, sd;
      ln_scalars(m, fmaxf(sq * (1.f / DM) - m * m, 0.f), mb, sd);
      const float inv = rcp(sd);
      rbest = (dt - mb * A1) * inv + A2;
      mm = pack_bf(mb, mb);
      ih = pack_bf(inv, inv);
      const float lo = inv - bf_lo(ih);
      il = pack_bf(lo, lo);
    }
    int ibest;
    {
      const uint32_t bits = __float_as_uint(rbest);
      const uint32_t key = (((int)bits < 0 ? ~bits : bits | 0x80000000u) & ~0x1ffu) | ((127 - lrow0 - (tq & 1) * 8) << 2) | tag;
      sts1(par + PAR_RED + warp * 4, __reduce_max_sync(0xffffffffu, key));
      PROF(8, ct == PT, 38); STAMP(7);
      uint32_t waited;
      asm volatile("{ .reg .pred p, q; setp.ne.u32 p, %1, 0; barrier.cta.red.or.pred q, 1, 256, p; selp.u32 %0, 1, 0, q; }" : "=r"(waited) : "r"((uint32_t)(wait1 && (wg || CW0))) : "memory");
      const uint4 ka = lds4(par + PAR_RED), kb = lds4(par + PAR_RED + 16);
      const uint32_t k2 = max(max(max(ka.x, ka.y), max(ka.z, ka.w)), max(max(kb.x, kb.y), max(kb.z, kb.w)));
      if (ct == 0 && ((cj & CWM) == 0 || (CWL && !waited))) st_relaxed(g_cand + rb, k2);
      ibest = 127 - ((k2 >> 2) & 127);
    }
    PROF(8, ct == PT, 39); STAMP(8);
    if ((ibest >> 4) == warp) {
      const int src = (ibest & 7) * 4 + ((ibest >> 3) & 1), ch = g * 2;
      const uint32_t cm = __shfl_sync(0xffffffffu, mm, src), ch_ = __shfl_sync(0xffffffffu, ih, src), cl = __shfl_sync(0xffffffffu, il, src);
      const uint32_t xa = res + (ch >> 3) * 16384 + ibest * 128 + (((ch & 7) ^ (ibest & 7)) << 4) + tq * 4;
      const uint32_t x0 = lds1(xa), x1 = lds1(xa ^ 16);
      const uint2 p0 = lds2(par + PAR_T2 + ch * 64 + tq * 16), p1 = lds2(par + PAR_T2 + ch * 64 + 64 + tq * 16);
      uint32_t* dst = g_row + rb * 2 * DM + cj * 128 + ln * 4;
      st_pairs(dst, ln_mod(x0, cm, ch_, cl, p0.x, p0.y), ln_mod(x1, cm, ch_, cl, p1.x, p1.y), tag);
      st_pairs(dst + DM, x0, x1, tag);
      __syncwarp();
    }
    PROF(8, ct == PT, 37); STAMP(9);
    uint32_t wd[64];
    const uint32_t wda = base + unit_of(FT_D, warp >> 1) + (warp & 1) * 8192 + frow * 128 + ((((ln >> 3) & 1) ^ (ln & 7)) << 4);
#define LOAD_WD(f) ldmatrix4t((wda ^ ((((f) >> 1) & 3) * 32)) + ((f) >> 3) * 4096 + ((f) & 1) * 2048, wd[4 * (f)], wd[4 * (f) + 1], wd[4 * (f) + 2], wd[4 * (f) + 3])
    if (!early) {
      if (b < NFFN) mbar_wait(bar_box + (warp >> 1) * 8, 0);
      LOAD_WF(0);
      __syncwarp();
      mbar_arrive_pred(bar_gate, lane0);
    }
    if (b < NFFN) {
      const uint32_t own = base + unit_of(FT_G, warp >> 1) + (warp & 1) * 8192;
      mbar_wait(bar_box + (4 + (warp >> 1)) * 8, 0);
      LOAD_WF(1);
      uint32_t* const ydst = g_ypart + ((size_t)(warp * 16 + tq * 2) * NFFN + b) * 8 + g;
      PROF(8, ct == PT, 31); STAMP(10);
      mbar_wait(bar_box + (8 + (warp >> 1)) * 8, 0);
#pragma unroll
      for (int f = 0; f < WDE; f++) LOAD_WD(f);
      STAMP(11);
      mbar_wait(bar_sel, 0);
      PROF(8, ct == PT, 33); STAMP(12);
      float d[8][4];
#pragma unroll
      for (int i = 0; i < 4; i++) { d[i][0] = 0.f; d[i][1] = 0.f; d[i][2] = 0.f; d[i][3] = 0.f; }
#pragma unroll
      for (int ks = 0; ks < 8; ks++) {
        const uint2 hb = lds2(own + 256 + ks * 32 + tq * 8);
#pragma unroll
        for (int mt = 0; mt < 4; mt++) {
          const int r = ks * 16 + mt * 4;
          mma16816(d[mt], wf[r], wf[r + 1], wf[r + 2], wf[r + 3], hb.x, hb.y);
        }
      }
      sts2(own + (tq * 8 + g) * 8, __float_as_uint((tq & 2) ? ((tq & 1) ? d[1][2] : d[1][0]) : ((tq & 1) ? d[0][2] : d[0][0])),
           __float_as_uint((tq & 2) ? ((tq & 1) ? d[3][2] : d[3][0]) : ((tq & 1) ? d[2][2] : d[2][0])));
      bar_sync(1, 256);
      uint32_t ab[4];
      {
        float G = 0.f, U = 0.f;
        uint2 pv[8];
#pragma unroll
        for (int w8 = 0; w8 < 8; w8++) pv[w8] = lds2(base + ln * 8 + ((FT_G >> (w8 >> 1) * 4) & 15) * UNIT + (w8 & 1) * 8192);
#pragma unroll
        for (int w8 = 0; w8 < 8; w8 += 2) {
          G += __uint_as_float(pv[w8].x) + __uint_as_float(pv[w8 + 1].x);
          U += __uint_as_float(pv[w8].y) + __uint_as_float(pv[w8 + 1].y);
        }
#pragma unroll
        for (int f = WDE; f < 16; f++) LOAD_WD(f);
        const float act = rbf(silu_f(rbf(G))) * rbf(U);
        const uint32_t pk = pack_bf(act, __shfl_down_sync(0xffffffffu, act, 1));
#pragma unroll
        for (int i = 0; i < 4; i++) ab[i] = __shfl_sync(0xffffffffu, pk, i * 8 + tq * 2);
      }
      PROF(8, ct == PT, 34); STAMP(13);
#pragma unroll
      for (int mt = 0; mt < 8; mt++) {
        d[mt][0] = 0.f; d[mt][1] = 0.f; d[mt][2] = 0.f; d[mt][3] = 0.f;
        mma16816(d[mt], wd[mt * 8], wd[mt * 8 + 1], wd[mt * 8 + 2], wd[mt * 8 + 3], ab[0], ab[1]);
        mma16816(d[mt], wd[mt * 8 + 4], wd[mt * 8 + 5], wd[mt * 8 + 6], wd[mt * 8 + 7], ab[2], ab[3]);
      }
#pragma unroll
      for (int i = 0; i < 4; i++) {
        const int m4 = (i >> 1) * 4, e = (i & 1) * 2;
        const float y = (tq & 2) ? ((tq & 1) ? d[m4 + 3][e] : d[m4 + 2][e]) : ((tq & 1) ? d[m4 + 1][e] : d[m4][e]);
        st_relaxed(ydst + (m4 * 2 + (i & 1)) * NFFN * 8, tagf(y, tag));
      }
      PROF(8, ct == PT, 35); STAMP(14);
    }
    mbar_wait(bar_sel, 0);
    mbar_arrive_pred(bar_win, ct == 0);
    const int iwin = lds1(par + PAR_CONST + 60) & 0x7ff;
    const bool cand = (iwin >> 4) == rb * 8 + warp;
    {
      const uint32_t mm0 = __shfl_sync(0xffffffffu, mm, ln & ~1), mm1 = __shfl_sync(0xffffffffu, mm, ln | 1);
      const uint32_t ih0 = __shfl_sync(0xffffffffu, ih, ln & ~1), ih1 = __shfl_sync(0xffffffffu, ih, ln | 1);
      const uint32_t il0 = __shfl_sync(0xffffffffu, il, ln & ~1), il1 = __shfl_sync(0xffffffffu, il, ln | 1);
#pragma unroll 1
      for (int hf = 0; hf < 2; hf++) {
        uint32_t x[16];
#pragma unroll
        for (int i = 0; i < 8; i += 2) ldmatrix4((trow ^ (i << 4)) + hf * 16384, x[2 * i], x[2 * i + 1], x[2 * i + 2], x[2 * i + 3]);
#pragma unroll
        for (int i = 0; i < 8; i++) {
          const uint4 pv = lds4(par + PAR_T2 + (hf * 8 + i) * 64 + tq * 16);
          x[2 * i] = hadd2(x[2 * i], hmul2(pv.z, ln_mod(x[2 * i], mm0, ih0, il0, pv.x, pv.y)));
          x[2 * i + 1] = hadd2(x[2 * i + 1], hmul2(pv.z, ln_mod(x[2 * i + 1], mm1, ih1, il1, pv.x, pv.y)));
        }
#pragma unroll
        for (int i = 0; i < 8; i += 2) stmatrix4((trow ^ (i << 4)) + hf * 16384, x[2 * i], x[2 * i + 1], x[2 * i + 2], x[2 * i + 3]);
      }
      if (!cand) fence_async_smem();
      __syncwarp();
      if (!cand && elect_one()) {
        tma2d_store(&maps.out, res + warp * 2048, cj * 128, rb * 128 + warp * 16);
        tma2d_store(&maps.out, res + 16384 + warp * 2048, cj * 128 + 64, rb * 128 + warp * 16);
        asm volatile("cp.async.bulk.commit_group;" ::: "memory");
      }
    }
    if (cand) {
      const int wrow0 = warp * 16;
#pragma unroll 2
      for (int p = 0; p < 8; p++) {
        const int row = 2 * p + (ln >> 4), ch = ln & 15;
        const uint4 v = lds4(res + (ch >> 3) * 16384 + (wrow0 + row) * 128 + (((ch & 7) ^ (row & 7)) << 4));
        if (rb * 128 + wrow0 + row != iwin) *reinterpret_cast<uint4*>(P.out + (size_t)(rb * 128 + wrow0 + row) * DM + cj * 128 + ch * 8) = v;
      }
    }
    asm volatile("cp.async.bulk.wait_group.read 0;" ::: "memory");
    PROF(8, ct == PT, 11); STAMP(15);
    cluster_wait();
  }
}

typedef CUresult (*EncodeFn)(CUtensorMap*, CUtensorMapDataType, cuuint32_t, void*, const cuuint64_t*, const cuuint64_t*,
                             const cuuint32_t*, const cuuint32_t*, CUtensorMapInterleave, CUtensorMapSwizzle,
                             CUtensorMapL2promotion, CUtensorMapFloatOOBfill);

void map2d(EncodeFn enc, CUtensorMap* m, const void* p, uint64_t rows, uint64_t cols, uint32_t brows) {
  cuuint64_t dims[2] = {cols, rows}, strides[1] = {cols * 2};
  cuuint32_t box[2] = {64, brows}, es[2] = {1, 1};
  enc(m, CU_TENSOR_MAP_DATA_TYPE_BFLOAT16, 2, const_cast<void*>(p), dims, strides, box, es, CU_TENSOR_MAP_INTERLEAVE_NONE,
      CU_TENSOR_MAP_SWIZZLE_128B, CU_TENSOR_MAP_L2_PROMOTION_L2_256B, CU_TENSOR_MAP_FLOAT_OOB_FILL_NONE);
}
void map2d_narrow(EncodeFn enc, CUtensorMap* m, const void* p, uint64_t rows, uint64_t cols, uint32_t brows) {
  cuuint64_t dims[2] = {cols, rows}, strides[1] = {cols * 2};
  cuuint32_t box[2] = {32, brows}, es[2] = {1, 1};
  enc(m, CU_TENSOR_MAP_DATA_TYPE_BFLOAT16, 2, const_cast<void*>(p), dims, strides, box, es, CU_TENSOR_MAP_INTERLEAVE_NONE,
      CU_TENSOR_MAP_SWIZZLE_64B, CU_TENSOR_MAP_L2_PROMOTION_L2_64B, CU_TENSOR_MAP_FLOAT_OOB_FILL_NONE);
}
void map3d(EncodeFn enc, CUtensorMap* m, const void* p, uint64_t rows, uint64_t cols, uint32_t brows, uint32_t nch) {
  cuuint64_t dims[3] = {64, rows, cols / 64}, strides[2] = {cols * 2, 128};
  cuuint32_t box[3] = {64, brows, nch}, es[3] = {1, 1, 1};
  enc(m, CU_TENSOR_MAP_DATA_TYPE_BFLOAT16, 3, const_cast<void*>(p), dims, strides, box, es, CU_TENSOR_MAP_INTERLEAVE_NONE,
      CU_TENSOR_MAP_SWIZZLE_128B, CU_TENSOR_MAP_L2_PROMOTION_L2_256B, CU_TENSOR_MAP_FLOAT_OOB_FILL_NONE);
}

}

extern "C" void kernel_launch(void* const* d_in, const int* in_sizes, int n_in, void* d_out, int out_size) {
  (void)in_sizes; (void)n_in; (void)out_size;
  static EncodeFn enc = nullptr;
  if (!enc) {
    void* fn = nullptr;
    cudaDriverEntryPointQueryResult st;
    cudaGetDriverEntryPoint("cuTensorMapEncodeTiled", &fn, cudaEnableDefault, &st);
    enc = (EncodeFn)fn;
    cudaFuncSetAttribute(fused_kernel, cudaFuncAttributeMaxDynamicSharedMemorySize, SMEM_BYTES);
  }
  Maps maps;
  map2d(enc, &maps.x, d_in[0], SEQ, DM, 128);
  map2d(enc, &maps.out, d_out, SEQ, DM, 16);
  map3d(enc, &maps.wq, d_in[3], DM, NQ, 64, 2);
  map3d(enc, &maps.k, d_in[1], 4 * SK, 128, 128, 1);
  map3d(enc, &maps.v, d_in[2], 4 * SK, 128, 128, 1);
  map3d(enc, &maps.wo, d_in[4], NQ, DM, 64, 2);
  map2d_narrow(enc, &maps.wg, d_in[7], DM, FF, 256);
  map2d_narrow(enc, &maps.wu, d_in[8], DM, FF, 256);
  map3d(enc, &maps.wd, d_in[9], FF, DM, 32, 4);
  map2d_narrow(enc, &maps.wm, d_in[11], DM, NMOD, 256);
  Ptrs p;
  p.x = (const __nv_bfloat16*)d_in[0];
  p.w_r = (const __nv_bfloat16*)d_in[6];
  p.w_gate = (const __nv_bfloat16*)d_in[7];
  p.w_up = (const __nv_bfloat16*)d_in[8];
  p.w_down = (const __nv_bfloat16*)d_in[9];
  p.c = (const __nv_bfloat16*)d_in[10];
  p.w_mod = (const __nv_bfloat16*)d_in[11];
  p.out = (__nv_bfloat16*)d_out;
  fused_kernel<<<NMAIN + NHELP, 384, SMEM_BYTES>>>(maps, p);
}
```

```cpp
#include <cuda_runtime.h>
#include <cuda_bf16.h>
#include <cuda.h>
#include <stdint.h>
#include <type_traits>

#define HD 2
#define HDX 2
#define NRS 8
#define FPACE 3
#define GOST 20
#define WB 2
#define WN 20
#define RES0 17
#define RES1 20
#define HU 32
#define NS1 6
#define PG0 15
#define PSL 0
#define CWM 7
#define WDE 16
#define CWL 1
#define CW0 0
#define ESV 1
#define PPOS 1
#define FB0 0
#define FB2 8
#define OPS 8192
#define OFL 0
#define ODS 8
#define MODUL hfma2
#define ODS1 5
#define VREL 5
#define E0 3

namespace {

constexpr int SEQ = 2048, DM = 1024, NQ = 4096, SK = 2048, WIN = 512, FF = 3584, NMOD = 6144;
constexpr int NMAIN = 128, NHELP = 4, NFFN = 112;
constexpr int NSLOT = 4, SLOT_BYTES = 32768, UNIT = 16384, GST_BYTES = 3 * UNIT;
constexpr uint32_t XT1 = 0xDCBA, XT2 = 0x9687;
constexpr uint32_t WT0 = 0xA741, WT1 = 0x7420, WT2 = 0x4A20;
constexpr uint32_t AT0 = WT1, AT1 = WT2;
constexpr uint32_t QT = 0xDC9696DC;
constexpr int OFF_STAGE = 12 * UNIT;
constexpr uint32_t FT_G = 0x07B3, FT_U = 0xA628, FT_D = 0x5149;
constexpr int OFF_RES = 12 * UNIT;
constexpr int OFF_PAR = 14 * UNIT;
constexpr int OFF_BAR = OFF_PAR + 2528;
constexpr int SMEM_BYTES = OFF_BAR + 544;
static_assert(SMEM_BYTES <= 232448, "smem");

constexpr int PAR_T1 = 0;
constexpr int PAR_T2 = 512;
constexpr int PAR_CONST = 1536;
constexpr int PAR_RED = 1600;
constexpr int PAR_SINK = 2176;

struct Maps {
  CUtensorMap x, wq, k, v, wo, wg, wu, wd, wm, out;
};
struct Ptrs {
  const __nv_bfloat16 *x, *w_r, *c, *w_mod, *w_gate, *w_up, *w_down;
  __nv_bfloat16* out;
};

__device__ __align__(1024) uint8_t g_act[16 * 80 * UNIT];
__device__ __align__(128) uint32_t g_mod[NMOD];
__device__ __align__(128) uint32_t g_modp[2 * 2 * DM];
__device__ __align__(128) uint32_t g_ln1[SEQ * 4];
__device__ __align__(128) uint32_t g_cnt_h[16 * 32];
__device__ __align__(128) uint32_t g_cnt_o[128 * 32];
__device__ __align__(128) uint32_t g_xch[NMAIN * 8 * 256 * 4];
__device__ __align__(128) uint32_t g_stats[8 * SEQ * 4];
__device__ __align__(128) uint32_t g_cand[32];
__device__ __align__(128) uint32_t g_row[16 * 2 * DM];
__device__ __align__(128) uint32_t g_ypart[NMAIN * NFFN * 8];
__device__ uint32_t g_epoch;

__device__ __forceinline__ uint32_t fresh_lane() { uint32_t l; asm volatile("mov.u32 %0, %%laneid;" : "=r"(l)); return l; }
__device__ __forceinline__ uint32_t frag_offset(int warp) {
  const uint32_t l = fresh_lane();
  return ((warp & 3) * 16 + (l & 15)) * 128 + (((l >> 4) ^ (l & 7)) << 4);
}
__device__ __forceinline__ bool elect_one() {
  uint32_t p;
  asm volatile("{ .reg .pred q; elect.sync _|q, 0xffffffff; selp.u32 %0, 1, 0, q; }" : "=r"(p));
  return p;
}
__device__ __forceinline__ uint32_t smem_u32(const void* p) { return (uint32_t)__cvta_generic_to_shared(p); }
__device__ __forceinline__ void mbar_init(uint32_t bar, uint32_t cnt) {
  asm volatile("mbarrier.init.shared::cta.b64 [%0], %1;" ::"r"(bar), "r"(cnt) : "memory");
}
__device__ __forceinline__ void mbar_expect_tx(uint32_t bar, uint32_t bytes) {
  asm volatile("mbarrier.arrive.expect_tx.shared::cta.b64 _, [%0], %1;" ::"r"(bar), "r"(bytes) : "memory");
}
__device__ __forceinline__ void mbar_arrive(uint32_t bar) {
  asm volatile("mbarrier.arrive.shared::cta.b64 _, [%0];" ::"r"(bar) : "memory");
}
__device__ __forceinline__ void mbar_arrive_pred(uint32_t bar, bool p) {
  asm volatile("{ .reg .pred p; setp.ne.b32 p, %1, 0; @p mbarrier.arrive.shared::cta.b64 _, [%0]; }" ::"r"(bar), "r"((int)p) : "memory");
}
__device__ __forceinline__ void mbar_arrive_cl(uint32_t bar, uint32_t off, bool p = true) {
  asm volatile("{ .reg .pred p, q; .reg .b32 a; setp.ne.b32 q, %2, 0; setp.ne.and.b32 p, %0, 0, q; add.u32 a, %0, %1; @p mbarrier.arrive.shared::cluster.b64 _, [a]; }"
               ::"r"(bar), "r"(off), "r"((int)p) : "memory");
}
__device__ __forceinline__ uint32_t mapa(uint32_t addr, uint32_t cta) {
  uint32_t r; asm("mapa.shared::cluster.u32 %0, %1, %2;" : "=r"(r) : "r"(addr), "r"(cta)); return r;
}
__device__ __forceinline__ void cluster_arrive() { asm volatile("barrier.cluster.arrive.relaxed.aligned;" ::: "memory"); }
__device__ __forceinline__ void cluster_wait() { asm volatile("barrier.cluster.wait.aligned;" ::: "memory"); }
__device__ __forceinline__ void watchdog(uint32_t& n) {
}
__device__ __forceinline__ void mbar_wait(uint32_t bar, uint32_t parity) {
  asm volatile("{\n.reg .pred p;\nWAIT_%=:\nmbarrier.try_wait.parity.shared::cta.b64 p, [%0], %1;\n@!p bra WAIT_%=;\n}" ::"r"(bar), "r"(parity) : "memory");
}
__device__ __forceinline__ bool mbar_test(uint32_t bar, uint32_t parity) {
  uint32_t ok;
  asm volatile("{\n.reg .pred p;\nmbarrier.test_wait.parity.shared::cta.b64 p, [%1], %2;\nselp.u32 %0, 1, 0, p;\n}" : "=r"(ok) : "r"(bar), "r"(parity) : "memory");
  return ok;
}
__device__ __forceinline__ uint64_t l2_stream() {
  uint64_t f; asm("createpolicy.fractional.L2::evict_first.b64 %0, 1.0;" : "=l"(f)); return f;
}
__device__ __forceinline__ void tma2d(uint32_t dst, const CUtensorMap* m, int c0, int c1, uint32_t bar) {
  asm volatile("cp.async.bulk.tensor.2d.shared::cluster.global.mbarrier::complete_tx::bytes.L2::cache_hint [%0], [%1, {%3, %4}], [%2], %5;"
               ::"r"(dst), "l"(m), "r"(bar), "r"(c0), "r"(c1), "l"(l2_stream()) : "memory");
}
__device__ __forceinline__ void bulk_load(uint32_t dst, const void* src, uint32_t bytes, uint32_t bar) {
  asm volatile("cp.async.bulk.shared::cluster.global.mbarrier::complete_tx::bytes [%0], [%1], %2, [%3];" ::"r"(dst), "l"(src), "r"(bytes), "r"(bar) : "memory");
}
__device__ __forceinline__ void bulk_load_stream(uint32_t dst, const void* src, uint32_t bytes, uint32_t bar) {
  asm volatile("cp.async.bulk.shared::cluster.global.mbarrier::complete_tx::bytes.L2::cache_hint [%0], [%1], %2, [%3], %4;"
               ::"r"(dst), "l"(src), "r"(bytes), "r"(bar), "l"(l2_stream()) : "memory");
}
__device__ __forceinline__ void tma2d_store(const CUtensorMap* m, uint32_t src, int c0, int c1) {
  asm volatile("cp.async.bulk.tensor.2d.global.shared::cta.bulk_group [%0, {%2, %3}], [%1];" ::"l"(m), "r"(src), "r"(c0), "r"(c1) : "memory");
}
__device__ __forceinline__ void bulk_store(void* dst, uint32_t src, uint32_t bytes) {
  asm volatile("cp.async.bulk.global.shared::cta.bulk_group [%0], [%1], %2;" ::"l"(dst), "r"(src), "r"(bytes) : "memory");
}
__device__ __forceinline__ uint32_t unit_of(uint32_t table, uint32_t i) { return ((table >> (i * 4)) & 15) * UNIT; }
__device__ __forceinline__ void tma3d(uint32_t dst, const CUtensorMap* m, int c0, int c1, int c2, uint32_t bar) {
  asm volatile("cp.async.bulk.tensor.3d.shared::cluster.global.mbarrier::complete_tx::bytes.L2::cache_hint [%0], [%1, {%3, %4, %5}], [%2], %6;"
               ::"r"(dst), "l"(m), "r"(bar), "r"(c0), "r"(c1), "r"(c2), "l"(l2_stream()) : "memory");
}
template <bool STREAM>
__device__ __forceinline__ void tma3d_mc(uint32_t dst, const CUtensorMap* m, int c0, int c1, int c2, uint32_t bar) {
  if (STREAM)
    asm volatile("cp.async.bulk.tensor.3d.shared::cluster.global.mbarrier::complete_tx::bytes.multicast::cluster.L2::cache_hint [%0], [%1, {%3, %4, %5}], [%2], %6, %7;"
                 ::"r"(dst), "l"(m), "r"(bar), "r"(c0), "r"(c1), "r"(c2), "h"((uint16_t)3), "l"(l2_stream()) : "memory");
  else
    asm volatile("cp.async.bulk.tensor.3d.shared::cluster.global.mbarrier::complete_tx::bytes.multicast::cluster [%0], [%1, {%3, %4, %5}], [%2], %6;"
                 ::"r"(dst), "l"(m), "r"(bar), "r"(c0), "r"(c1), "r"(c2), "h"((uint16_t)3) : "memory");
}
__device__ __forceinline__ void prefetch_map(const CUtensorMap* m) {
  asm volatile("prefetch.tensormap [%0];" ::"l"(m) : "memory");
}
__device__ __forceinline__ void fence_async() { asm volatile("fence.proxy.async.global;" ::: "memory"); }
__device__ __forceinline__ void fence_async_smem() { asm volatile("fence.proxy.async.shared::cta;" ::: "memory"); }
__device__ __forceinline__ void bar_sync(int id, int n) { asm volatile("bar.sync %0, %1;" ::"r"(id), "r"(n) : "memory"); }
__device__ __forceinline__ void bar_arrive(int id, int n) { asm volatile("bar.arrive %0, %1;" ::"r"(id), "r"(n) : "memory"); }
__device__ __forceinline__ void wg_fence() { asm volatile("wgmma.fence.sync.aligned;" ::: "memory"); }
__device__ __forceinline__ void wg_commit() { asm volatile("wgmma.commit_group.sync.aligned;" ::: "memory"); }
template <int N> __device__ __forceinline__ void wg_wait() { asm volatile("wgmma.wait_group.sync.aligned %0;" ::"n"(N) : "memory"); }
__device__ __forceinline__ uint64_t make_desc(uint32_t addr, uint32_t lbo, uint32_t sbo) {
  return (uint64_t)((addr & 0x3FFFF) >> 4) | ((uint64_t)(lbo >> 4) << 16) | ((uint64_t)(sbo >> 4) << 32) | (1ull << 62);
}
__device__ __forceinline__ uint32_t ld_relaxed(const uint32_t* p) {
  uint32_t v; asm volatile("ld.relaxed.gpu.global.u32 %0, [%1];" : "=r"(v) : "l"(p) : "memory"); return v;
}
__device__ __forceinline__ uint32_t ld_acquire(const uint32_t* p) {
  uint32_t v; asm volatile("ld.acquire.gpu.global.u32 %0, [%1];" : "=r"(v) : "l"(p) : "memory"); return v;
}
__device__ __forceinline__ uint4 ld_relaxed4(const uint32_t* p) {
  uint4 v; asm volatile("ld.relaxed.gpu.global.v4.u32 {%0,%1,%2,%3}, [%4];" : "=r"(v.x), "=r"(v.y), "=r"(v.z), "=r"(v.w) : "l"(p) : "memory"); return v;
}
__device__ __forceinline__ uint2 ld_relaxed2(const uint32_t* p) {
  uint2 v; asm volatile("ld.relaxed.gpu.global.v2.u32 {%0,%1}, [%2];" : "=r"(v.x), "=r"(v.y) : "l"(p) : "memory"); return v;
}
__device__ __forceinline__ void st_relaxed(uint32_t* p, uint32_t v) {
  asm volatile("st.relaxed.gpu.global.u32 [%0], %1;" ::"l"(p), "r"(v) : "memory");
}
__device__ __forceinline__ void st_relaxed2(uint32_t* p, uint32_t a, uint32_t b) {
  asm volatile("st.relaxed.gpu.global.v2.u32 [%0], {%1,%2};" ::"l"(p), "r"(a), "r"(b) : "memory");
}
__device__ __forceinline__ void st_relaxed4(uint32_t* p, uint32_t a, uint32_t b, uint32_t c, uint32_t d) {
  asm volatile("st.relaxed.gpu.global.v4.u32 [%0], {%1,%2,%3,%4};" ::"l"(p), "r"(a), "r"(b), "r"(c), "r"(d) : "memory");
}
__device__ __forceinline__ void st_b128(uint32_t* p, uint32_t a, uint32_t b, uint32_t c, uint32_t d) {
  asm volatile("{ .reg .b64 u, v; .reg .b128 w; mov.b64 u, {%1, %2}; mov.b64 v, {%3, %4}; mov.b128 w, {u, v}; st.relaxed.gpu.global.b128 [%0], w; }"
               ::"l"(p), "r"(a), "r"(b), "r"(c), "r"(d) : "memory");
}
__device__ __forceinline__ uint4 ld_b128(const uint32_t* p) {
  uint4 r;
  asm volatile("{ .reg .b64 u, v; .reg .b128 w; ld.relaxed.gpu.global.b128 w, [%4]; mov.b128 {u, v}, w; mov.b64 {%0, %1}, u; mov.b64 {%2, %3}, v; }"
               : "=r"(r.x), "=r"(r.y), "=r"(r.z), "=r"(r.w) : "l"(p) : "memory");
  return r;
}
__device__ __forceinline__ void st_pairs(uint32_t* p, uint32_t a, uint32_t b, uint32_t tag) {
  asm volatile("{ .reg .b64 u, v; mov.b64 u, {%1, %3}; mov.b64 v, {%2, %3}; st.relaxed.gpu.global.v2.b64 [%0], {u, v}; }"
               ::"l"(p), "r"(a), "r"(b), "r"(tag) : "memory");
}
__device__ __forceinline__ uint4 ld_pairs(const uint32_t* p) {
  uint4 v;
  asm volatile("{ .reg .b64 u, v; ld.relaxed.gpu.global.v2.b64 {u, v}, [%4]; mov.b64 {%0, %1}, u; mov.b64 {%2, %3}, v; }"
               : "=r"(v.x), "=r"(v.y), "=r"(v.z), "=r"(v.w) : "l"(p) : "memory");
  return v;
}
__device__ __forceinline__ uint2 ld_pair(const uint32_t* p) {
  uint2 v;
  asm volatile("{ .reg .b64 u; ld.relaxed.gpu.global.b64 u, [%2]; mov.b64 {%0, %1}, u; }" : "=r"(v.x), "=r"(v.y) : "l"(p) : "memory");
  return v;
}
__device__ __forceinline__ void red_release(uint32_t* p, uint32_t v) {
  asm volatile("red.release.gpu.global.add.u32 [%0], %1;" ::"l"(p), "r"(v) : "memory");
}
__device__ __forceinline__ uint32_t ldg_nc1(const void* p) {
  uint32_t v;
  asm volatile("ld.global.nc.u32 %0, [%1];" : "=r"(v) : "l"(p));
  return v;
}
__device__ __forceinline__ uint4 ldg_nc4(const void* p) {
  uint4 v; asm volatile("ld.global.nc.L1::no_allocate.v4.u32 {%0,%1,%2,%3}, [%4];" : "=r"(v.x), "=r"(v.y), "=r"(v.z), "=r"(v.w) : "l"(p)); return v;
}
__device__ __forceinline__ uint4 ldg_stream4(const void* p) {
  uint4 v;
  asm volatile("ld.global.nc.L1::no_allocate.L2::cache_hint.v4.u32 {%0,%1,%2,%3}, [%4], %5;" : "=r"(v.x), "=r"(v.y), "=r"(v.z), "=r"(v.w) : "l"(p), "l"(l2_stream()));
  return v;
}
__device__ __forceinline__ void stg4(void* p, uint4 v) {
  asm volatile("st.global.v4.u32 [%0], {%1,%2,%3,%4};" ::"l"(p), "r"(v.x), "r"(v.y), "r"(v.z), "r"(v.w) : "memory");
}
__device__ __forceinline__ void wait_counter(const uint32_t* p, uint32_t target) {
  uint32_t n = 0;
  while (__any_sync(0xffffffffu, (int)(ld_acquire(p) - target) < 0)) { watchdog(n); }
}
__device__ __forceinline__ uint32_t tagf(float v, uint32_t tag) { return (__float_as_uint(v) & ~3u) | tag; }
__device__ __forceinline__ bool tag_ok(uint4 v, uint32_t tag) { return (((v.x ^ tag) | (v.y ^ tag) | (v.z ^ tag) | (v.w ^ tag)) & 3u) == 0; }
__device__ __forceinline__ float untag_sum(uint32_t a, uint32_t b) { return __uint_as_float(a & ~3u) + __uint_as_float(b & ~3u); }
__device__ __forceinline__ uint4 poll4(const uint32_t* p, uint32_t tag) {
  uint4 v = ld_relaxed4(p);
  uint32_t n = 0;
  while (!__all_sync(0xffffffffu, tag_ok(v, tag))) { v = ld_relaxed4(p); watchdog(n); }
  return v;
}
__device__ __forceinline__ float bf_lo(uint32_t v) { return __uint_as_float(v << 16); }
__device__ __forceinline__ float bf_hi(uint32_t v) { return __uint_as_float(v & 0xffff0000u); }
__device__ __forceinline__ uint32_t pack_bf(float lo, float hi) {
  uint32_t r; asm("cvt.rn.bf16x2.f32 %0, %1, %2;" : "=r"(r) : "f"(hi), "f"(lo)); return r;
}
__device__ __forceinline__ float rbf(float v) { return __uint_as_float(pack_bf(0.f, v) & 0xffff0000u); }
__device__ __forceinline__ uint32_t hmul2(uint32_t a, uint32_t b) {
  uint32_t r; asm("mul.rn.bf16x2 %0, %1, %2;" : "=r"(r) : "r"(a), "r"(b)); return r;
}
__device__ __forceinline__ uint32_t hadd2(uint32_t a, uint32_t b) {
  uint32_t r; asm("add.rn.bf16x2 %0, %1, %2;" : "=r"(r) : "r"(a), "r"(b)); return r;
}
__device__ __forceinline__ uint32_t hsub2(uint32_t a, uint32_t b) {
  uint32_t r; asm("sub.rn.bf16x2 %0, %1, %2;" : "=r"(r) : "r"(a), "r"(b)); return r;
}
__device__ __forceinline__ uint32_t hmax2(uint32_t a, uint32_t b) {
  uint32_t r; asm("max.bf16x2 %0, %1, %2;" : "=r"(r) : "r"(a), "r"(b)); return r;
}
__device__ __forceinline__ float rcp(float x) { float r; asm("rcp.approx.ftz.f32 %0, %1;" : "=f"(r) : "f"(x)); return r; }
__device__ __forceinline__ float ex2(float x) { float r; asm("ex2.approx.ftz.f32 %0, %1;" : "=f"(r) : "f"(x)); return r; }
__device__ __forceinline__ void stmatrix4(uint32_t addr, uint32_t a, uint32_t b, uint32_t c, uint32_t d) {
  asm volatile("stmatrix.sync.aligned.m8n8.x4.shared.b16 [%0], {%1,%2,%3,%4};" ::"r"(addr), "r"(a), "r"(b), "r"(c), "r"(d) : "memory");
}
__device__ __forceinline__ void ldmatrix4(uint32_t addr, uint32_t& a, uint32_t& b, uint32_t& c, uint32_t& d) {
  asm volatile("ldmatrix.sync.aligned.m8n8.x4.shared.b16 {%0,%1,%2,%3}, [%4];" : "=r"(a), "=r"(b), "=r"(c), "=r"(d) : "r"(addr) : "memory");
}
__device__ __forceinline__ void ldmatrix4t(uint32_t addr, uint32_t& a, uint32_t& b, uint32_t& c, uint32_t& d) {
  asm volatile("ldmatrix.sync.aligned.m8n8.x4.trans.shared.b16 {%0,%1,%2,%3}, [%4];" : "=r"(a), "=r"(b), "=r"(c), "=r"(d) : "r"(addr) : "memory");
}
__device__ __forceinline__ void mma16816(float (&d)[4], uint32_t a0, uint32_t a1, uint32_t a2, uint32_t a3, uint32_t b0, uint32_t b1) {
  asm volatile("mma.sync.aligned.m16n8k16.row.col.f32.bf16.bf16.f32 {%0,%1,%2,%3}, {%4,%5,%6,%7}, {%8,%9}, {%0,%1,%2,%3};"
               : "+f"(d[0]), "+f"(d[1]), "+f"(d[2]), "+f"(d[3]) : "r"(a0), "r"(a1), "r"(a2), "r"(a3), "r"(b0), "r"(b1));
}
__device__ __forceinline__ void sts1(uint32_t a, uint32_t v) { asm volatile("st.shared.u32 [%0], %1;" ::"r"(a), "r"(v) : "memory"); }
__device__ __forceinline__ uint4 lds4(uint32_t a) {
  uint4 v; asm volatile("ld.shared.v4.u32 {%0,%1,%2,%3}, [%4];" : "=r"(v.x), "=r"(v.y), "=r"(v.z), "=r"(v.w) : "r"(a) : "memory"); return v;
}
__device__ __forceinline__ uint2 lds2(uint32_t a) {
  uint2 v; asm volatile("ld.shared.v2.u32 {%0,%1}, [%2];" : "=r"(v.x), "=r"(v.y) : "r"(a) : "memory"); return v;
}
__device__ __forceinline__ uint32_t lds1(uint32_t a) {
  uint32_t v; asm volatile("ld.shared.u32 %0, [%1];" : "=r"(v) : "r"(a) : "memory"); return v;
}
__device__ __forceinline__ void sts2(uint32_t a, uint32_t x, uint32_t y) { asm volatile("st.shared.v2.u32 [%0], {%1,%2};" ::"r"(a), "r"(x), "r"(y) : "memory"); }
__device__ __forceinline__ void sts4(uint32_t a, uint4 v) {
  asm volatile("st.shared.v4.u32 [%0], {%1,%2,%3,%4};" ::"r"(a), "r"(v.x), "r"(v.y), "r"(v.z), "r"(v.w) : "memory");
}
__device__ __forceinline__ float silu_f(float v) { return __fdividef(v, 1.f + __expf(-v)); }
__device__ __forceinline__ uint32_t hfma2(uint32_t a, uint32_t b, uint32_t c) {
  uint32_t r; asm("fma.rn.bf16x2 %0, %1, %2, %3;" : "=r"(r) : "r"(a), "r"(b), "r"(c)); return r;
}
__device__ __forceinline__ void split_inv(float sd, uint32_t& ih, uint32_t& il) {
  const float inv = rcp(sd);
  ih = pack_bf(inv, inv);
  const float lo = inv - bf_lo(ih);
  il = pack_bf(lo, lo);
}
__device__ __forceinline__ uint32_t ln_norm(uint32_t x, uint32_t mean2, uint32_t ih, uint32_t il) {
  const uint32_t d = hsub2(x, mean2);
  return hfma2(d, ih, hmul2(d, il));
}
__device__ __forceinline__ uint32_t modul(uint32_t n, uint32_t c1, uint32_t sh) { return hadd2(hmul2(n, c1), sh); }
__device__ __forceinline__ uint32_t ln_mod(uint32_t x, uint32_t mean2, uint32_t ih, uint32_t il, uint32_t c1, uint32_t sh) {
  return modul(ln_norm(x, mean2, ih, il), c1, sh);
}

#define R8(a, i) "+f"(a[i]), "+f"(a[i + 1]), "+f"(a[i + 2]), "+f"(a[i + 3]), "+f"(a[i + 4]), "+f"(a[i + 5]), "+f"(a[i + 6]), "+f"(a[i + 7])
#define D64 "{%0,%1,%2,%3,%4,%5,%6,%7,%8,%9,%10,%11,%12,%13,%14,%15,%16,%17,%18,%19,%20,%21,%22,%23,%24,%25,%26,%27,%28,%29,%30,%31," \
            "%32,%33,%34,%35,%36,%37,%38,%39,%40,%41,%42,%43,%44,%45,%46,%47,%48,%49,%50,%51,%52,%53,%54,%55,%56,%57,%58,%59,%60,%61,%62,%63}"
template <int TB>
__device__ __forceinline__ void mma_ss(float (&d)[64], uint64_t da, uint64_t db, int sc) {
  asm volatile("{\n.reg .pred p;\nsetp.ne.b32 p, %66, 0;\n"
               "wgmma.mma_async.sync.aligned.m64n128k16.f32.bf16.bf16 " D64 ", %64, %65, p, 1, 1, 0, %67;\n}"
               : R8(d, 0), R8(d, 8), R8(d, 16), R8(d, 24), R8(d, 32), R8(d, 40), R8(d, 48), R8(d, 56)
               : "l"(da), "l"(db), "r"(sc), "n"(TB));
}
template <int TB>
__device__ __forceinline__ void mma_rs(float (&d)[64], uint32_t a0, uint32_t a1, uint32_t a2, uint32_t a3, uint64_t db, int sc) {
  asm volatile("{\n.reg .pred p;\nsetp.ne.b32 p, %69, 0;\n"
               "wgmma.mma_async.sync.aligned.m64n128k16.f32.bf16.bf16 " D64 ", {%64,%65,%66,%67}, %68, p, 1, 1, %70;\n}"
               : R8(d, 0), R8(d, 8), R8(d, 16), R8(d, 24), R8(d, 32), R8(d, 40), R8(d, 48), R8(d, 56)
               : "r"(a0), "r"(a1), "r"(a2), "r"(a3), "l"(db), "r"(sc), "n"(TB));
}
#define D128 "{%0,%1,%2,%3,%4,%5,%6,%7,%8,%9,%10,%11,%12,%13,%14,%15,%16,%17,%18,%19,%20,%21,%22,%23,%24,%25,%26,%27,%28,%29,%30,%31," \
             "%32,%33,%34,%35,%36,%37,%38,%39,%40,%41,%42,%43,%44,%45,%46,%47,%48,%49,%50,%51,%52,%53,%54,%55,%56,%57,%58,%59,%60,%61,%62,%63," \
             "%64,%65,%66,%67,%68,%69,%70,%71,%72,%73,%74,%75,%76,%77,%78,%79,%80,%81,%82,%83,%84,%85,%86,%87,%88,%89,%90,%91,%92,%93,%94,%95," \
             "%96,%97,%98,%99,%100,%101,%102,%103,%104,%105,%106,%107,%108,%109,%110,%111,%112,%113,%114,%115,%116,%117,%118,%119,%120,%121,%122,%123,%124,%125,%126,%127}"
#define R128(d, e) R8(d, 0), R8(d, 8), R8(d, 16), R8(d, 24), R8(d, 32), R8(d, 40), R8(d, 48), R8(d, 56), \
                   R8(e, 0), R8(e, 8), R8(e, 16), R8(e, 24), R8(e, 32), R8(e, 40), R8(e, 48), R8(e, 56)
__device__ __forceinline__ void mma256_ss(float (&d)[64], float (&e)[64], uint64_t da, uint64_t db, int sc) {
  asm volatile("{\n.reg .pred p;\nsetp.ne.b32 p, %130, 0;\n"
               "wgmma.mma_async.sync.aligned.m64n256k16.f32.bf16.bf16 " D128 ", %128, %129, p, 1, 1, 0, 1;\n}"
               : R128(d, e) : "l"(da), "l"(db), "r"(sc));
}
__device__ __forceinline__ void mma256_rs(float (&d)[64], float (&e)[64], uint32_t a0, uint32_t a1, uint32_t a2, uint32_t a3, uint64_t db) {
  asm volatile("{\n.reg .pred p;\nsetp.ne.b32 p, 1, 0;\n"
               "wgmma.mma_async.sync.aligned.m64n256k16.f32.bf16.bf16 " D128 ", {%128,%129,%130,%131}, %132, p, 1, 1, 1;\n}"
               : R128(d, e) : "r"(a0), "r"(a1), "r"(a2), "r"(a3), "l"(db));
}
template <int N> __device__ __forceinline__ void keep(float (&a)[N]) {
#pragma unroll
  for (int i = 0; i < N; i++) asm volatile("" : "+f"(a[i])::"memory");
}
template <int N> __device__ __forceinline__ void keep(uint32_t (&a)[N]) {
#pragma unroll
  for (int i = 0; i < N; i++) asm volatile("" : "+r"(a[i])::"memory");
}

#define STAMP(idx) do {} while (0)
#define PROF(grp, cond, idx) do {} while (0)

constexpr float SCL2 = 1.4426950408889634f * 0.08838834764831845f;

__device__ __forceinline__ void pack_p(const float (&s)[64], uint32_t (&p)[32]) {
#pragma unroll
  for (int i = 0; i < 32; i++) p[i] = pack_bf(s[2 * i], s[2 * i + 1]);
}

__device__ __forceinline__ void issue_qk(float (&s)[64], uint32_t q0, uint32_t q1, uint32_t kslot) {
  const uint64_t db = make_desc(kslot, 16, 1024), da0 = make_desc(q0, 16, 1024), da1 = make_desc(q1, 16, 1024);
#pragma unroll
  for (int kk = 0; kk < 8; kk++) mma_ss<0>(s, (kk < 4 ? da0 : da1) + (kk & 3) * 2, db + (kk >> 2) * 1024 + (kk & 3) * 2, kk != 0);
}
__device__ __forceinline__ void issue_pv(float (&o)[64], uint32_t (&p)[32], uint32_t vslot, int acc) {
  uint64_t db = make_desc(vslot, 16384, 1024);
#pragma unroll
  for (int kk = 0; kk < 8; kk++)
    mma_rs<1>(o, p[4 * kk], p[4 * kk + 1], p[4 * kk + 2], p[4 * kk + 3], db + kk * 128, kk == 0 ? acc : 1);
}

template <int H>
__device__ __forceinline__ void store_chunk(const float (&a)[64], uint32_t addr) {
#pragma unroll
  for (int i = 8 * H; i < 8 * H + 8; i += 2)
    stmatrix4(addr ^ ((i & 7) << 4), pack_bf(a[4 * i], a[4 * i + 1]), pack_bf(a[4 * i + 2], a[4 * i + 3]),
              pack_bf(a[4 * i + 4], a[4 * i + 5]), pack_bf(a[4 * i + 6], a[4 * i + 7]));
}
template <int H>
__device__ __forceinline__ void store_chunk(const float (&a)[64], float i0, float i1, uint32_t addr) {
#pragma unroll
  for (int i = 8 * H; i < 8 * H + 8; i += 2)
    stmatrix4(addr ^ ((i & 7) << 4), pack_bf(a[4 * i] * i0, a[4 * i + 1] * i0), pack_bf(a[4 * i + 2] * i1, a[4 * i + 3] * i1),
              pack_bf(a[4 * i + 4] * i0, a[4 * i + 5] * i0), pack_bf(a[4 * i + 6] * i1, a[4 * i + 7] * i1));
}
__device__ __forceinline__ float inv_quad_sum(float l) {
  l += __shfl_xor_sync(0xffffffffu, l, 1);
  l += __shfl_xor_sync(0xffffffffu, l, 2);
  return rcp(l);
}

__device__ __forceinline__ void ln_scalars(float mean, float var, float& mb, float& sd) {
  mb = rbf(mean);
  float r; asm("sqrt.approx.ftz.f32 %0, %1;" : "=f"(r) : "f"(rbf(rbf(var) + 1e-5f)));
  sd = rbf(r);
}

__global__ void __cluster_dims__(2, 1, 1) __launch_bounds__(384, 1) fused_kernel(const __grid_constant__ Maps maps, const Ptrs P) {
  extern __shared__ __align__(1024) uint8_t smem_raw[];
  const uint32_t base = smem_u32(smem_raw);
  const int tid = threadIdx.x, lane = tid & 31;
  const int warp = __shfl_sync(0xffffffffu, tid >> 5, 0);
  const int b = blockIdx.x;
  PROF(31, tid == 0, 0);

  if (b >= NMAIN) {
    float* sc = reinterpret_cast<float*>(smem_raw);
    float* red = sc + DM;
    for (int k = tid; k < DM; k += 384) sc[k] = rbf(silu_f(__bfloat162float(P.c[k])));
    __syncthreads();
    if (tid < 256) {
      const int col = 2048 + (b - NMAIN) * 1024 + (tid & 127) * 8, r0 = (tid >> 7) * 512;
      float acc[8];
#pragma unroll
      for (int e = 0; e < 8; e++) acc[e] = 0.f;
#pragma unroll 1
      for (int r = r0; r < r0 + 512; r += HU) {
        uint4 w[HU];
#pragma unroll
        for (int u = 0; u < HU; u++) w[u] = ldg_stream4(P.w_mod + (size_t)(r + u) * NMOD + col);
#pragma unroll
        for (int u = 0; u < HU; u++) {
          float s = sc[r + u];
          acc[0] += s * bf_lo(w[u].x); acc[1] += s * bf_hi(w[u].x); acc[2] += s * bf_lo(w[u].y); acc[3] += s * bf_hi(w[u].y);
          acc[4] += s * bf_lo(w[u].z); acc[5] += s * bf_hi(w[u].z); acc[6] += s * bf_lo(w[u].w); acc[7] += s * bf_hi(w[u].w);
        }
      }
      if (tid >= 128) {
#pragma unroll
        for (int e = 0; e < 8; e++) red[(tid & 127) * 8 + e] = acc[e];
      }
      const uint32_t tag = ld_relaxed(&g_epoch) % 3 + 1;
      bar_sync(1, 256);
      if (tid < 128) {
        uint32_t o[8];
#pragma unroll
        for (int e = 0; e < 8; e++) o[e] = __float_as_uint(rbf(acc[e] + red[tid * 8 + e])) | tag;
        st_relaxed4(g_mod + col, o[0], o[1], o[2], o[3]);
        st_relaxed4(g_mod + col + 4, o[4], o[5], o[6], o[7]);
        const uint4 wr = ldg_nc4(P.w_r + tid * 8);
        const uint32_t wv[4] = {wr.x, wr.y, wr.z, wr.w};
        float dsum = 0.f;
#pragma unroll
        for (int e = 0; e < 8; e++) {
          const float m = bf_hi(o[e]);
          dsum += (b == NMAIN + 2 ? rbf(1.f + m) : m) * ((e & 1) ? bf_hi(wv[e >> 1]) : bf_lo(wv[e >> 1]));
        }
#pragma unroll
        for (int k = 16; k > 0; k >>= 1) dsum += __shfl_xor_sync(0xffffffffu, dsum, k);
        if (lane == 0) st_relaxed(g_mod + (b - NMAIN) * 4 + warp, tagf(dsum, tag));
      }
    }
    PROF(2, tid == 0, 1);
    return;
  }

  const int rank = b & 1;
  const int rb = ((b >> 4) << 1) | rank, cj = (b >> 1) & 7;
  const uint32_t bfull = base + OFF_BAR, bempty = bfull + NSLOT * 8;
  const uint32_t gfull = bempty + NSLOT * 8, gempty = gfull + 32;
  const uint32_t bar_ofull = gempty + 32;
  const uint32_t bar_ofree = bar_ofull + 32;
  const uint32_t bar_par = bar_ofree + 32;
  const uint32_t bar_mod = bar_par + 8;
  const uint32_t bar_pread = bar_mod + 8;
  const uint32_t bar_xres = bar_pread + 8;
  const uint32_t bar_ring = bar_xres + 8;
  const uint32_t bar_box = bar_ring + 24;
  const uint32_t bar_go = bar_box + 96;
  const uint32_t bar_go2 = bar_go + 16;
  const uint32_t bar_cnt = bar_go + 24;
  const uint32_t xfull = bar_go + 40, xempty = xfull + 32;
  const uint32_t bar_hw = xempty + 32, bar_hx = bar_hw + 8;
  const uint32_t bar_hpub = bar_hx + 16;
  const uint32_t bar_win = bar_hpub + 16;
  const uint32_t bar_rx = bar_win + 8;
  const uint32_t bar_sel = bar_rx + 8;
  const uint32_t bar_gate = bar_sel + 8;
  const uint32_t bar_rel = bar_gate + 8;
  const uint32_t bar_od = bar_rel + 8;
  const uint32_t bar_res = bar_go + 8;
  const uint32_t stage = base + OFF_STAGE, par = base + OFF_PAR;

  if (warp == 8 && elect_one()) {
    for (int s = 0; s < NSLOT; s++) { mbar_init(bfull + s * 8, 1); mbar_init(bempty + s * 8, 16); }
    for (int s = 0; s < 4; s++) { mbar_init(gfull + s * 8, 1); mbar_init(gempty + s * 8, 16); mbar_init(xfull + s * 8, 1); mbar_init(xempty + s * 8, 8); mbar_init(bar_ofree + s * 8, 1); mbar_init(bar_ofull + s * 8, 128); }
    mbar_init(bar_par, 64); mbar_init(bar_mod, 256); mbar_init(bar_pread, 2); mbar_init(bar_xres, 1);
    mbar_init(bar_ring, 8); mbar_init(bar_ring + 8, 8); mbar_init(bar_ring + 16, 8);
    mbar_init(bar_go, 1); mbar_init(bar_go2, 1); mbar_init(bar_cnt, 1); mbar_init(bar_cnt + 8, 1); mbar_init(bar_hpub, 8); mbar_init(bar_hpub + 8, 8); mbar_init(bar_res, 1); mbar_init(bar_win, 1); mbar_init(bar_rx, 1); mbar_init(bar_sel, 64); mbar_init(bar_gate, 8); mbar_init(bar_rel, 8); mbar_init(bar_od, 1);
    for (int s = 0; s < 12; s++) mbar_init(bar_box + s * 8, 1);
    asm volatile("fence.mbarrier_init.release.cluster;" ::: "memory");
    prefetch_map(&maps.x); prefetch_map(&maps.wq); prefetch_map(&maps.k); prefetch_map(&maps.v);
  }
  if (warp == 9 && elect_one()) {
    mbar_init(bar_hw, 1); mbar_init(bar_hx, 1); mbar_init(bar_hx + 8, 1);
    asm volatile("fence.mbarrier_init.release.cluster;" ::: "memory");
    mbar_expect_tx(bar_hw, 32768);
    mbar_expect_tx(bar_hx, 16384);
    mbar_expect_tx(bar_hx + 8, 16384);
    const __nv_bfloat16* xs = P.x + (size_t)(rb * 128 + cj * 16) * DM;
    bulk_load(base + 2 * GST_BYTES, xs, 16384, bar_hx);
    tma2d(stage, &maps.wm, (b >> 1) * 32, rank * 512, bar_hw);
    tma2d(stage + 16384, &maps.wm, (b >> 1) * 32, rank * 512 + 256, bar_hw);
    bulk_load(base + 3 * GST_BYTES, xs + 8 * DM, 16384, bar_hx + 8);
  }
  cluster_arrive();

  if (warp >= 8) {
    asm volatile("setmaxnreg.dec.sync.aligned.u32 40;");
    if (warp < 10) bar_arrive(1, 320);
    const uint32_t epoch = ld_relaxed(&g_epoch);
    cluster_wait();
    if (warp == 8) {
      const int kvrow = (cj >> 1) * SK + (SK - WIN);
      int wch = cj * 8 + rank * 2;
#pragma unroll 1
      for (int ps = 0; ps < 3; ps++) {
        const CUtensorMap* mw = ps == 2 ? &maps.wo : &maps.wq;
        const uint32_t xt = ps == 1 ? XT1 : XT2, wt = ps == 0 ? WT0 : (ps == 1 ? WT1 : WT2);
        const int nst = ps == 2 ? 32 : 16;
#pragma unroll 1
        for (int i = 0; i < nst; i++) {
          const uint32_t bf = gfull + (i & 3) * 8;
          const int kt = ps == 2 ? (((cj & 1) * 4 + ((i >> 1) & 3)) * 4 + (i >> 3)) * 2 + (i & 1) : (i + (ps ? 0 : b & 14)) & 15;
          const uint32_t wd = base + unit_of(wt, i & 3) + rank * UNIT, xd = base + unit_of(xt, i & 3);
          const uint8_t* xs = g_act + (uint32_t)(rb * 80 + (ps - 1) * 16 + kt) * UNIT;
          if (ps == 0 && i == HD) mbar_wait(bar_mod, 0);
          const bool xfirst = ps && i < 2;
          if (ps == 2 && i == 0) mbar_wait(bar_ofree + 24, 0);
          if (i == 0) fence_async();
          mbar_wait(gempty + (i & 3) * 8, ((i >> 2) & 1) ^ 1);
          if (elect_one()) {
            mbar_expect_tx(bf, ps ? GST_BYTES : 2 * UNIT);
            if (xfirst) bulk_load_stream(xd, xs, UNIT, bf);
          }
          if (ps && i < 4) mbar_wait(bempty + i * 8, 1);
          if (elect_one()) tma3d_mc<true>(wd, mw, 0, (i == 31 ? kt ^ (rank * 32) : kt) * 64, i == 31 ? cj * 2 : wch, bf);
          if (ps) {
            if (i == 16 || i == 24) { mbar_wait(bar_cnt + i - 16, 0); fence_async(); }
            if (i == RES0) mbar_wait(bar_res, 0);
            if (i == 2) mbar_wait(bar_ofree + (ps - 1) * 16, 0);
            if (elect_one()) {
              if (i == 31) bulk_load(xd, xs, UNIT, bf); else if (!xfirst) bulk_load_stream(xd, xs, UNIT, bf);
              mbar_arrive_pred(bar_go, i == GOST - 1);
              if (PG0 < 16) mbar_arrive_pred(bar_go2, ps == 1 && i == PG0);
              mbar_arrive_pred(bar_od, i == (ps == 1 ? ODS1 : ODS));
              if (i == RES0) mbar_expect_tx(bar_xres, 32768);
              if (i == RES0 || i == RES1) tma2d(base + OFF_RES + (i == RES1) * UNIT, &maps.x, cj * 128 + (i == RES1) * 64, rb * 128, bar_xres);
            }
          }
        }
        if (ps == 2) break;
        wch = ps ? ((wch >> 3) ^ rank) * 2 : wch + 4;
#pragma unroll 1
        for (int u = 0; u < 16; u++) {
          const bool isk = (u == 0) || ((u & 1) && u < 15);
          const int blk = (isk ? (u + 1) >> 1 : (u == 15 ? 7 : (u >> 1) - 1)) & 3;
          const uint32_t sl = base + unit_of(ps ? AT1 : AT0, u & 3) + rank * UNIT, bf = bfull + (u & 3) * 8;
          if (u < 4) mbar_wait(gempty + ((u + 1) >> 1) * 8, 1);
          mbar_wait(bempty + (u & 3) * 8, ((u >> 2) & 1) ^ 1);
          if (elect_one()) {
            mbar_arrive_pred(bar_go2, ps && u + 16 == PG0);
            mbar_expect_tx(bf, SLOT_BYTES);
            tma3d_mc<false>(sl, isk ? &maps.k : &maps.v, 0, kvrow + blk * 128, rank, bf);
          }
        }
      }
      if (elect_one()) mbar_expect_tx(bar_rx, UNIT);
      mbar_wait(bar_rel, 0);
      if (elect_one()) {
        bulk_load_stream(base + UNIT, g_act + (uint32_t)(rb * 80 + 16 + 63 - (cj & 1) * 32) * UNIT, UNIT, bar_rx);
      }
      if (b < NFFN) {
#pragma unroll 1
        for (int u = 0; u < 12; u++) {
          const uint32_t dst = base + unit_of(u < 4 ? FT_G : (u < 8 ? FT_U : FT_D), u & 3);
          if (elect_one()) mbar_expect_tx(bar_box + u * 8, UNIT);
          if (u == FB0 || u == 2 || u == FB2) mbar_wait(bar_ring + (u == FB2 ? 16 : (u + 6) & 8), 0);
          if (u >= FPACE) mbar_wait(bar_box + (u - FPACE) * 8, 0);
          if (elect_one()) {
            if (u < 8) tma2d(dst, u < 4 ? &maps.wg : &maps.wu, b * 32, (u & 3) * 256, bar_box + u * 8);
            else tma3d(dst, &maps.wd, 0, b * 32, (u - 8) * 4, bar_box + u * 8);
          }
        }
      }
    } else if (warp == 9) {
      const uint32_t target = 8 * (epoch + 1);
      uint32_t hmask = 0;
#pragma unroll 1
      for (int i = 0; i < 16; i++) {
        if (i == HDX) mbar_wait(bar_mod, 0);
        const uint32_t need = i == 15 ? 0xffffu : 1u << ((2 * cj + i) & 15);
        if (i >= NRS && (hmask & need) != need) {
          uint32_t n = 0;
          do { hmask = __ballot_sync(0xffffffffu, ld_acquire(&g_cnt_h[rb * 32 + (lane & 15)]) == epoch + 1); watchdog(n); } while ((hmask & need) != need);
          PROF(1, lane == 0 && i == NRS, 26);
          fence_async();
        }
        mbar_wait(xempty + (i & 3) * 8, ((i >> 2) & 1) ^ 1);
        if (elect_one()) {
          mbar_expect_tx(xfull + (i & 3) * 8, UNIT);
          if (i < NRS) tma2d(base + (i & 3) * GST_BYTES, &maps.x, ((2 * cj + i) & 15) * 64, rb * 128, xfull + (i & 3) * 8);
          else bulk_load_stream(base + (i & 3) * GST_BYTES, g_act + (uint32_t)(rb * 80 + ((2 * cj + i) & 15)) * UNIT, UNIT, xfull + (i & 3) * 8);
        }
      }
      prefetch_map(&maps.wo);
#pragma unroll 1
      for (int t = 0; t < 4; t++) {
        if (t & 1) mbar_wait(bar_od, t >> 1);
#pragma unroll 1
        for (int p = 0; p < 32768 / OPS; p++) {
          const uint32_t w = p / (16384 / OPS), c = (p / (8192 / OPS)) & 1, off = w * 8192 + (p % (8192 / OPS)) * OPS;
          mbar_wait(bar_ofull + (t & 1) * 16 + w * 8, t >> 1);
          if (elect_one()) {
            bulk_store(g_act + (uint32_t)(rb * 80 + 16 + (cj * 4 + t) * 2 + c) * UNIT + off, base + unit_of(QT, 2 * t + c) + off, OPS);
            asm volatile("cp.async.bulk.commit_group;" ::: "memory");
            asm volatile("cp.async.bulk.wait_group.read %0;" ::"n"(OFL) : "memory");
          }
        }
        if (elect_one()) {
          asm volatile("cp.async.bulk.wait_group.read 0;" ::: "memory");
          mbar_arrive(t < 3 ? bar_ofree + t * 8 : bar_res);
          asm volatile("cp.async.bulk.wait_group 0;" ::: "memory");
          fence_async();
          red_release(&g_cnt_o[((rb * 4 + t) * 2 + (cj >> 2)) * 32], 2);
        }
        if (t) {
          wait_counter(&g_cnt_o[(rb * 8 + 2 * t + (cj & 1)) * 32], target);
          if (t & 1) wait_counter(&g_cnt_o[(rb * 8 + (t == 1 ? cj & 1 : 7 - (cj & 1))) * 32], target);
          if (elect_one()) mbar_arrive(t == 1 ? bar_ofree + 24 : bar_cnt + t * 8 - 16);
        }
      }
      PROF(2, lane == 0, 27);
      const uint32_t tag = epoch % 3 + 1;
      const uint32_t* inbox = g_cand + (lane & 15);
      mbar_wait(bar_ring + 16, 0);
      uint32_t c0 = ld_relaxed(inbox), n = 0;
#define CAND_STEP(cv)                                                                                        \
      {                                                                                                      \
        const bool valid = (cv & 3u) == tag, all = __all_sync(0xffffffffu, valid);                           \
        const uint32_t best = __reduce_max_sync(0xffffffffu, valid ? cv : 0u);                               \
        const uint32_t blk = __ffs(__ballot_sync(0xffffffffu, cv == best)) - 1;                              \
        if (best) sts2(par + PAR_CONST + 56, best, (blk << 7 | (~best >> 2 & 127)) | (all ? 0x1800 : 0x800)); \
        if (all) break;                                                                                      \
        cv = ld_relaxed(inbox);                                                                              \
      }
      while (true) { CAND_STEP(c0) watchdog(n); }
    } else {
      const int t2 = tid - 320;
      mbar_wait(bar_hpub + (warp & 1) * 8, 0);
      PROF(1, t2 == 0, 24);
#pragma unroll 1
      for (int c = 0; c < 8; c++) {
        const uint32_t off = (warp & 1) * UNIT + c * 2048 + lane * 16;
        uint8_t* dst = g_act + (uint32_t)(rb * 80 + cj * 2) * UNIT + off;
        const uint4 v0 = lds4(stage + off), v1 = lds4(stage + off + 512), v2 = lds4(stage + off + 1024), v3 = lds4(stage + off + 1536);
        stg4(dst, v0); stg4(dst + 512, v1); stg4(dst + 1024, v2); stg4(dst + 1536, v3);
      }
      __syncwarp();
      PROF(1, t2 == 0, 15);
      if (lane == 0) {
        mbar_arrive(bar_pread);
        red_release(&g_cnt_h[rb * 32 + cj * 2 + (warp & 1)], 1);
        PROF(1, t2 == 0, 25);
        prefetch_map(&maps.wg); prefetch_map(&maps.wu); prefetch_map(&maps.wd); prefetch_map(&maps.out);
      }
      __syncwarp();
      if (b < NFFN) {
        mbar_wait(bar_go2, 0);
        const __nv_bfloat16* pg = ((b & 1) ? P.w_up : P.w_gate) + (b >> 1) * 64 + (size_t)t2 * FF;
        const __nv_bfloat16* pd = P.w_down + (size_t)b * 32768 + t2 * 64;
        PROF(2, t2 == 0, 13);
#pragma unroll 1
        for (int i = 0; i < WN; i += WB) {
          uint32_t v[WB];
#pragma unroll
          for (int u = 0; u < WB; u++) {
            const int k = i + u;
            asm volatile("ld.global.cg.L2::128B.u32 %0, [%1];" : "=r"(v[u]) : "l"(k < 16 ? pg + (size_t)k * 64 * FF : pd + (k - 16) * 4096));
          }
#pragma unroll
          for (int u = 1; u < WB; u++) v[0] ^= v[u];
          sts1(par + PAR_SINK + t2 * 4, v[0]);
        }
        PROF(2, t2 == 0, 14);
      }
      const uint32_t tag = epoch % 3 + 1;
      mbar_wait(bar_go, 0);
      if (warp == 10) {
        const uint32_t* src = g_mod + 2 * DM + cj * 128 + lane * 4;
        const uint2 wr = *reinterpret_cast<const uint2*>(P.w_r + cj * 128 + lane * 4);
        uint4 vga, vsb, vcb, vgb;
        uint32_t n = 0;
        do {
          vga = ld_relaxed4(src); vsb = ld_relaxed4(src + DM); vcb = ld_relaxed4(src + 2 * DM); vgb = ld_relaxed4(src + 3 * DM);
          watchdog(n);
        } while (!__all_sync(0xffffffffu, tag_ok(vga, tag) && tag_ok(vsb, tag) && tag_ok(vcb, tag) && tag_ok(vgb, tag)));
        const float c0 = rbf(1.f + bf_hi(vcb.x)), c1 = rbf(1.f + bf_hi(vcb.y)), c2 = rbf(1.f + bf_hi(vcb.z)), c3 = rbf(1.f + bf_hi(vcb.w));
        const float a0 = c0 * bf_lo(wr.x), a1 = c1 * bf_hi(wr.x), a2 = c2 * bf_lo(wr.y), a3 = c3 * bf_hi(wr.y);
        const uint32_t h0 = pack_bf(a0, a1), h1 = pack_bf(a2, a3);
        const uint32_t t1 = par + PAR_T1 + (lane >> 2) * 64 + (lane & 1) * 32 + (lane & 2) * 2;
        sts1(t1, h0); sts1(t1 + 8, pack_bf(a0 - bf_lo(h0), a1 - bf_hi(h0)));
        sts1(t1 + 16, h1); sts1(t1 + 24, pack_bf(a2 - bf_lo(h1), a3 - bf_hi(h1)));
        sts4(par + PAR_T2 + lane * 32, make_uint4(pack_bf(c0, c1), __byte_perm(vsb.x, vsb.y, 0x7632), __byte_perm(vgb.x, vgb.y, 0x7632), __byte_perm(vga.x, vga.y, 0x7632)));
        sts4(par + PAR_T2 + lane * 32 + 16, make_uint4(pack_bf(c2, c3), __byte_perm(vsb.z, vsb.w, 0x7632), __byte_perm(vgb.z, vgb.w, 0x7632), __byte_perm(vga.z, vga.w, 0x7632)));
      } else {
        const uint4 g = poll4((lane & 2) ? g_mod + 8 - (lane & 1) * 4 : g_mod + 5 * DM + b * 8 + (lane & 1) * 4, tag);
        sts1(par + PAR_CONST + 60, 0);
        if (lane < 2) sts4(par + PAR_CONST + 16 + lane * 16, g);
        else if (lane < 4) sts2(par + PAR_CONST + (lane - 2) * 8, __float_as_uint(untag_sum(g.x, g.y) + untag_sum(g.z, g.w)), epoch);
      }
      __syncwarp();
#pragma unroll 4
      for (int q = 0; q < 32; q++) st_b128(g_xch + ((size_t)b * 8 * 256 + q * 64 + t2) * 4, (epoch & 1) << 16, 0, 0, 0);
      for (int q = 0; q < 2; q++) st_relaxed4(g_stats + ((size_t)cj * SEQ + rb * 128 + q * 64 + t2) * 4, 0, 0, 0, 0);
      if (b < NFFN)
        for (int q = 0; q < 4; q++) st_relaxed4(g_ypart + ((size_t)(q * 32 + (t2 >> 1)) * NFFN + b) * 8 + (t2 & 1) * 4, 0, 0, 0, 0);
      st_relaxed4(g_row + rb * 2 * DM + (t2 >> 5) * DM + cj * 128 + (t2 & 31) * 4, 0, 0, 0, 0);
      __threadfence();
      mbar_arrive(bar_par);
      mbar_wait(bar_gate, 0);
      uint32_t have = 0, n = 0;
      while (true) {
        const uint32_t st = lds1(par + PAR_CONST + 60) >> 7;
        if ((st & 31) != have) {
          const uint32_t* hsrc = g_row + (st & 15) * 2 * DM + t2 * 4;
          uint4 hv[4];
          bool ok = true;
#pragma unroll
          for (int i = 0; i < 4; i++) hv[i] = ld_pairs(hsrc + i * 256);
#pragma unroll
          for (int i = 0; i < 4; i++) {
            sts2(base + ((FT_G >> i * 4) & 15) * UNIT + (warp & 1) * 8192 + 256 + lane * 8, hv[i].x, hv[i].z);
            ok = ok && hv[i].y == tag && hv[i].w == tag;
          }
          have = __all_sync(0xffffffffu, ok) ? st & 31 : 0;
        }
        if ((st ^ have) == 32) break;
        watchdog(n);
      }
      mbar_arrive(bar_sel);
    }
    __syncwarp();
    cluster_arrive();
    {
      const uint32_t tag = epoch % 3 + 1, t3 = tid - 256;
      mbar_wait(bar_win, 0);
      uint2 win = lds2(par + PAR_CONST + 56);
      win.y &= 0x7ff;
      const uint32_t* fsrc = g_row + (win.y >> 7) * 2 * DM + (b >> 1) * 16 + (t3 & 3) * 4 + (b & 1) * 2;
      const uint32_t* ysrc = g_ypart + (size_t)b * NFFN * 8 + min(t3, NFFN - 1) * 4;
      uint2 fh = ld_pair(fsrc), fx = ld_pair(fsrc + DM);
      if (PSL) __nanosleep(PSL);
      uint4 ya = ld_relaxed4(ysrc), yb = ld_relaxed4(ysrc + NFFN * 4);
      const float rwin = __uint_as_float(((int)win.x < 0 ? win.x & 0x7fffffffu : ~win.x) & ~0x1ffu);
      const float rs = rbf(rcp(1.f + __expf(-rbf(rwin))));
      uint32_t n = 0;
      while (__any_sync(0xffffffffu, fh.y != tag || fx.y != tag)) { fh = ld_pair(fsrc); fx = ld_pair(fsrc + DM); watchdog(n); }
      while (!__all_sync(0xffffffffu, tag_ok(ya, tag) && tag_ok(yb, tag))) {
        if (!tag_ok(ya, tag)) ya = ld_relaxed4(ysrc);
        if (!tag_ok(yb, tag)) yb = ld_relaxed4(ysrc + NFFN * 4);
        watchdog(n);
      }
      __syncwarp();
      PROF(8, t3 == 0, 5);
      float y0 = untag_sum(ya.x, yb.x), y1 = untag_sum(ya.y, yb.y), y2 = untag_sum(ya.z, yb.z), y3 = untag_sum(ya.w, yb.w);
      const bool u1 = lane & 2, u2 = lane & 4;
      y0 = (u1 ? y2 : y0) + __shfl_xor_sync(0xffffffffu, u1 ? y0 : y2, 2);
      y1 = (u1 ? y3 : y1) + __shfl_xor_sync(0xffffffffu, u1 ? y1 : y3, 2);
      y0 = (u2 ? y1 : y0) + __shfl_xor_sync(0xffffffffu, u2 ? y0 : y1, 4);
      y0 += __shfl_xor_sync(0xffffffffu, y0, 8);
      if (!(lane & 8)) sts1(par + PAR_RED + 64 + (t3 >> 4) * 32 + ((lane & 1) * 4 + (lane & 2) + ((lane >> 2) & 1)) * 4, __float_as_uint(y0));
      bar_sync(4, 128);
      if (t3 < 4) {
        y0 = 0.f; y1 = 0.f;
#pragma unroll
        for (int w4 = 0; w4 < 7; w4++) {
          const uint2 v = lds2(par + PAR_RED + 64 + w4 * 32 + t3 * 8);
          y0 += __uint_as_float(v.x); y1 += __uint_as_float(v.y);
        }
        const uint2 gv = lds2(par + PAR_CONST + 16 + t3 * 8);
        const uint32_t upd = hmul2(pack_bf(y0, y1), pack_bf(rs, rs));
        *reinterpret_cast<uint32_t*>(P.out + (size_t)win.y * DM + b * 8 + t3 * 2) =
            hadd2(fx.x, hmul2(__byte_perm(gv.x, gv.y, 0x7632), hadd2(fh.x, upd)));
        if (b == 0 && t3 == 0) st_relaxed(&g_epoch, epoch + 1);
      }
      PROF(31, t3 == 0, 36);
    }
    cluster_wait();
  } else {
    const int wg = warp >> 2;

    uint32_t tag;
    {
      uint32_t* const pmod = g_modp + rank * 2 * DM + (b >> 1) * 32 + lane;
      uint32_t* const pln = g_ln1 + (rb * 128 + cj * 16 + warp) * 4;
      const uint32_t cv = ldg_nc1(P.c + rank * 512 + tid * 2);
      const uint32_t epoch = ld_relaxed(&g_epoch);
      if (warp == 0) st_relaxed(pmod, 0);
      if (lane == 0) { st_b128(pln, 0, 0, 0, 0); st_b128(pln + 32, 0, 0, 0, 0); }
      asm volatile("setmaxnreg.inc.sync.aligned.u32 232;");
      sts1(par + tid * 4, pack_bf(silu_f(bf_lo(cv)), silu_f(bf_hi(cv))));
      bar_sync(1, 320);
      tag = epoch % 3 + 1;
#pragma unroll
      for (int part = 0; part < 3; part++) {
        if (part != 1) {
          const uint32_t xa = base + (2 + part / 2) * GST_BYTES + warp * 2048 + lane * 16;
          mbar_wait(bar_hx + part * 4, 0);
          float s0 = 0.f, s1 = 0.f, q0 = 0.f, q1 = 0.f;
#pragma unroll
          for (int q = 0; q < 4; q++) {
            const uint4 xv = lds4(xa + q * 512);
            const uint32_t u[4] = {xv.x, xv.y, xv.z, xv.w};
#pragma unroll
            for (int e = 0; e < 4; e++) { const float lo = bf_lo(u[e]), hi = bf_hi(u[e]); s0 += lo; s1 += hi; q0 += lo * lo; q1 += hi * hi; }
          }
          s0 += s1; q0 += q1;
#pragma unroll
          for (int o = 16; o > 0; o >>= 1) { s0 += __shfl_xor_sync(0xffffffffu, s0, o); q0 += __shfl_xor_sync(0xffffffffu, q0, o); }
          const float mean = s0 * (1.f / DM);
          float mb, sd;
          ln_scalars(mean, fmaxf(q0 * (1.f / DM) - mean * mean, 0.f), mb, sd);
          uint32_t ih, il;
          split_inv(sd, ih, il);
          if (lane == 0) st_b128(pln + part * 16, pack_bf(mb, mb), ih, il, tag);
          PROF(1, tid == 0 && part == 2, 4);
        } else {
          const uint32_t fr = (lane & 7) + (lane >> 4) * 8, tq = lane & 3;
          const uint32_t wa = stage + warp * 4096 + fr * 64 + ((((lane >> 3) & 1) ^ ((fr >> 1) & 3)) << 4);
          uint32_t sc[8];
#pragma unroll
          for (int k = 0; k < 8; k++) sc[k] = lds1(par + warp * 128 + k * 16 + tq * 4);
          float d0[4] = {0.f, 0.f, 0.f, 0.f}, d1[4] = {0.f, 0.f, 0.f, 0.f};
          mbar_wait(bar_hw, 0);
#pragma unroll
          for (int ks = 0; ks < 4; ks++) {
            uint32_t w[8];
            ldmatrix4t(wa + ks * 1024, w[0], w[1], w[2], w[3]);
            ldmatrix4t((wa ^ 32) + ks * 1024, w[4], w[5], w[6], w[7]);
            mma16816(d0, w[0], w[1], w[2], w[3], sc[2 * ks], sc[2 * ks + 1]);
            mma16816(d1, w[4], w[5], w[6], w[7], sc[2 * ks], sc[2 * ks + 1]);
          }
          sts1(base + 2 * GST_BYTES + warp * 2048 + (tq * 8 + (lane >> 2)) * 4, __float_as_uint((tq & 2) ? ((tq & 1) ? d1[2] : d1[0]) : ((tq & 1) ? d0[2] : d0[0])));
          bar_sync(1, 256);
          if (warp == 0) {
            float s = 0.f;
#pragma unroll
            for (int w8 = 0; w8 < 8; w8++) s += __uint_as_float(lds1(base + 2 * GST_BYTES + w8 * 2048 + lane * 4));
            st_relaxed(pmod, (__float_as_uint(s) & ~3u) | tag);
          }
          PROF(1, tid == 0, 3);
        }
      }
      cluster_wait();
      if (wg == 1) bar_arrive(2, 256);
    }

    float f0 = 0.f, f1 = 0.f;
    const uint32_t rempty = lane < 2 ? mapa(bempty, lane & 1) : 0;
    constexpr uint32_t GE = NSLOT * 8 + 32;
    float o[64], s[64];
#pragma unroll 1
    for (int ps = 0; ps < 3; ps++) {
      {
        const uint32_t xt = ps == 1 ? XT1 : XT2, wt = ps == 1 ? WT1 : WT2;
        const int nst = ps == 2 ? 28 : 14;
        if (ps == 0) {
          float ga[64], gb[64];
#pragma unroll
          for (int i = 0; i < 64; i++) { ga[i] = 0.f; gb[i] = 0.f; }
          uint32_t a[2][16];
          const uint32_t l = fresh_lane();
          uint32_t fa[4];
#pragma unroll
          for (int kk = 0; kk < 4; kk++) fa[kk] = (base + wg * 8192 + frag_offset(warp)) ^ (kk * 32);
          const uint32_t mt = par + (l & 3) * 16;
          auto fetch = [&](int i, uint32_t (&f)[16], uint32_t z) {
            mbar_wait(xfull + (i & 3) * 8, i >> 2);
#pragma unroll
            for (int kk = 0; kk < 4; kk++) ldmatrix4(fa[kk] + (i & 3) * GST_BYTES + z, f[4 * kk], f[4 * kk + 1], f[4 * kk + 2], f[4 * kk + 3]);
          };
          uint4 r0, r1;
          {
            const uint32_t t7 = (warp & 3) * 32 + l;
            const uint32_t* pm = g_modp + wg * DM + ((cj * 128 + t7 * 4) & (DM - 1));
            const uint32_t* pr = g_ln1 + (rb * 128 + warp * 16 + (l >> 2)) * 4;
            uint4 m0 = ld_relaxed4(pm), m1 = ld_relaxed4(pm + 2 * DM);
            r0 = ld_b128(pr); r1 = ld_b128(pr + 32);
            fetch(0, a[0], 0); fetch(1, a[1], 0);
            uint32_t n = 0;
            bool written = false;
#pragma unroll 1
            while (true) {
              uint32_t miss;
              asm volatile("{ .reg .pred p0, p1, p2, p3; .reg .b32 t, u;\n"
                           "lop3.b32 t, %1, %2, %19, 0x7e; lop3.b32 u, %3, %4, %19, 0x7e; or.b32 t, t, u; and.b32 t, t, 3; setp.ne.u32 p0, t, 0;\n"
                           "lop3.b32 t, %5, %6, %19, 0x7e; lop3.b32 u, %7, %8, %19, 0x7e; or.b32 t, t, u; and.b32 t, t, 3; setp.ne.u32 p1, t, 0;\n"
                           "setp.ne.u32 p2, %12, %19; setp.ne.u32 p3, %16, %19;\n"
                           "@p0 ld.relaxed.gpu.global.v4.u32 {%1, %2, %3, %4}, [%17];\n"
                           "@p1 ld.relaxed.gpu.global.v4.u32 {%5, %6, %7, %8}, [%17 + 8192];\n"
                           "@p2 ld.relaxed.gpu.global.v4.u32 {%9, %10, %11, %12}, [%18];\n"
                           "@p3 ld.relaxed.gpu.global.v4.u32 {%13, %14, %15, %16}, [%18 + 128];\n"
                           "or.pred p0, p0, p1; or.pred p2, p2, p3; vote.sync.any.pred p0, p0, 0xffffffff; vote.sync.any.pred p2, p2, 0xffffffff;\n"
                           "selp.u32 t, 1, 0, p0; selp.u32 u, 2, 0, p2; or.b32 %0, t, u; }"
                           : "=r"(miss), "+r"(m0.x), "+r"(m0.y), "+r"(m0.z), "+r"(m0.w), "+r"(m1.x), "+r"(m1.y), "+r"(m1.z), "+r"(m1.w),
                             "+r"(r0.x), "+r"(r0.y), "+r"(r0.z), "+r"(r0.w), "+r"(r1.x), "+r"(r1.y), "+r"(r1.z), "+r"(r1.w)
                           : "l"(pm), "l"(pr), "r"(tag) : "memory");
              if (!(miss & 1) && !written) {
                written = true;
                float c0 = untag_sum(m0.x, m1.x), c1 = untag_sum(m0.y, m1.y), c2 = untag_sum(m0.z, m1.z), c3 = untag_sum(m0.w, m1.w);
                if (wg) { c0 = 1.f + rbf(c0); c1 = 1.f + rbf(c1); c2 = 1.f + rbf(c2); c3 = 1.f + rbf(c3); }
                const uint32_t d = par + (t7 >> 2) * 64 + (t7 & 1) * 32 + (t7 & 2) * 2 + (wg ? 0 : 8);
                sts1(d, pack_bf(c0, c1));
                sts1(d + 16, pack_bf(c2, c3));
                mbar_arrive(bar_mod);
              }
              if (!miss) break;
              watchdog(n);
            }
          }
          const uint32_t zero = r0.w ^ tag;
          auto normalize = [&](uint32_t (&f)[16]) {
#pragma unroll
            for (int k = 0; k < 16; k += 2) { f[k] = ln_norm(f[k], r0.x, r0.y, r0.z); f[k + 1] = ln_norm(f[k + 1], r1.x, r1.y, r1.z); }
          };
          auto modulate = [&](int i, uint32_t (&f)[16]) {
#pragma unroll
            for (int kk = 0; kk < 4; kk++) {
              const uint4 m = lds4(mt + i * 256 + kk * 64);
              f[4 * kk] = MODUL(f[4 * kk], m.x, m.z); f[4 * kk + 1] = MODUL(f[4 * kk + 1], m.x, m.z);
              f[4 * kk + 2] = MODUL(f[4 * kk + 2], m.y, m.w); f[4 * kk + 3] = MODUL(f[4 * kk + 3], m.y, m.w);
            }
            keep(f);
            mbar_arrive_pred(xempty + (i & 3) * 8, l == 0);
          };
          auto publish = [&](int u, uint32_t (&f)[16]) {
#pragma unroll
            for (int kk = 0; kk < 4; kk++) stmatrix4(fa[kk] + OFF_STAGE + u * UNIT, f[4 * kk], f[4 * kk + 1], f[4 * kk + 2], f[4 * kk + 3]);
            __syncwarp();
            mbar_arrive_pred(bar_hpub + u * 8, l == 0);
          };
          auto multiply = [&](int i, uint32_t (&f)[16]) {
            mbar_wait(gfull + (i & 3) * 8, i >> 2);
            const uint64_t db = make_desc(base + (i & 3) * GST_BYTES + UNIT, 8192, 1024);
            wg_fence();
#pragma unroll
            for (int kk = 0; kk < 4; kk++) mma256_rs(ga, gb, f[4 * kk], f[4 * kk + 1], f[4 * kk + 2], f[4 * kk + 3], db + kk * 128);
            wg_commit();
          };
          auto next = [&](int i, uint32_t (&f)[16]) {
            wg_wait<1>();
            mbar_arrive_cl(rempty, GE + ((i + 2) & 3) * 8);
            uint32_t z = zero;
#pragma unroll
            for (int k = 0; k < 16; k += 2) asm volatile("lop3.b32 %0, %1, %2, %0, 0xA8;" : "+r"(z) : "r"(f[k]), "r"(f[k + 1]));
            fetch(i, f, z);
            normalize(f); modulate(i, f); multiply(i, f);
          };
          normalize(a[0]); normalize(a[1]);
          keep(a[0]); keep(a[1]);
          mbar_wait(bar_mod, 0);
          PROF(1, tid == 0, 2);
          modulate(0, a[0]); multiply(0, a[0]); publish(0, a[0]);
          modulate(1, a[1]); multiply(1, a[1]); publish(1, a[1]);
#pragma unroll 1
          for (int i = 2; i < NRS; i += 2) { next(i, a[0]); next(i + 1, a[1]); }
          wg_wait<1>();
          mbar_arrive_cl(rempty, GE + ((NRS + 2) & 3) * 8);
#pragma unroll 1
          for (int i = NRS; i < 14; i++) {
            mbar_wait(xfull + (i & 3) * 8, (i >> 2) & 1);
            mbar_wait(gfull + (i & 3) * 8, (i >> 2) & 1);
            const uint32_t xa = base + (i & 3) * GST_BYTES;
            const uint64_t da = make_desc(xa + wg * 8192, 16, 1024), db = make_desc(xa + UNIT, 8192, 1024);
            if (i == 13) bar_sync(2 + wg, 256);
            wg_fence();
#pragma unroll
            for (int kk = 0; kk < 4; kk++) mma256_ss(ga, gb, da + kk * 2, db + kk * 128, 1);
            wg_commit();
            if (i == 13) bar_arrive(3 - wg, 256);
            wg_wait<1>();
            uint32_t z = zero;
#pragma unroll
            for (int k = 0; k < 16; k += 2) asm volatile("lop3.b32 %0, %1, %2, %0, 0xA8;" : "+r"(z) : "r"(a[1][k]), "r"(a[1][k + 1]));
            mbar_arrive_cl(rempty, GE + ((i + 3) & 3) * 8 + z);
            mbar_arrive_pred(xempty + ((i + 3) & 3) * 8, l == 0 && i != NRS);
          }
          mbar_wait(xfull + 16, 1);
          wg_wait<0>();
          keep(ga); keep(gb);
#pragma unroll
          for (int i = 0; i < 64; i++) {
            asm volatile("mov.b32 %0, %1;" : "=f"(s[i]) : "f"(ga[i]));
            asm volatile("mov.b32 %0, %1;" : "=f"(o[i]) : "f"(gb[i]));
          }
        } else {
          float ga[64], gb[64];
#pragma unroll
          for (int i = 0; i < 64; i++) {
            asm volatile("mov.b32 %0, %1;" : "=f"(ga[i]) : "f"(s[i]));
            asm volatile("mov.b32 %0, %1;" : "=f"(gb[i]) : "f"(o[i]));
          }
#pragma unroll 1
          for (int i = 0; i < nst; i++) {
            mbar_wait(gfull + (i & 3) * 8, (i >> 2) & 1);
            const uint64_t da = make_desc(base + unit_of(xt, i & 3) + wg * 8192, 16, 1024), db = make_desc(base + unit_of(wt, i & 3), 8192, 1024);
            if (i == nst - 1) bar_sync(2 + wg, 256);
            wg_fence();
#pragma unroll
            for (int kk = 0; kk < 4; kk++) mma256_ss(ga, gb, da + kk * 2, db + kk * 128, kk ? 1 : i);
            wg_commit();
            if (i == nst - 1) bar_arrive(3 - wg, 256);
            wg_wait<1>();
            mbar_arrive_cl(rempty, GE + ((i + 3) & 3) * 8, i != 0);
            PROF(4, tid == 0 && (i & 3) == 0, 40 + (ps - 1) * 4 + i / 4);
          }
          wg_wait<0>();
          keep(ga); keep(gb);
#pragma unroll
          for (int i = 0; i < 64; i++) {
            asm volatile("mov.b32 %0, %1;" : "=f"(s[i]) : "f"(ga[i]));
            asm volatile("mov.b32 %0, %1;" : "=f"(o[i]) : "f"(gb[i]));
          }
        }
        mbar_arrive_cl(rempty, GE + (ps == 2 ? 24 : 8));
        if (ps == 2) break;
      }
      const uint32_t qw = base + wg * 8192, qt = QT >> (16 * ps), at = ps ? AT1 : AT0;
      {
        const uint32_t wt = ps ? WT1 : WT0;
        const uint64_t da0 = make_desc(qw + unit_of(qt, 2), 16, 1024), da1 = make_desc(qw + unit_of(qt, 3), 16, 1024);
        const uint64_t db0 = make_desc(base + unit_of(wt, 2), 8192, 1024), db1 = make_desc(base + unit_of(wt, 3), 8192, 1024);
        mbar_wait(gfull + 16, 1);
        bar_sync(2 + wg, 256);
        wg_fence();
#pragma unroll
        for (int kk = 0; kk < 4; kk++) mma_ss<1>(s, da0 + kk * 2, db0 + kk * 128, 1);
        wg_commit();
        mbar_wait(xfull + 24, 1);
        mbar_wait(gfull + 24, 1);
        wg_fence();
#pragma unroll
        for (int kk = 0; kk < 4; kk++) mma_ss<1>(s, da1 + kk * 2, db1 + kk * 128, 1);
        wg_commit();
        bar_arrive(3 - wg, 256);
        mbar_wait(ps == 0 ? bar_pread : bar_ofree + 8, 0);
        wg_wait<0>();
        keep(s);
        PROF(2, tid == 0, 8 + ps * 8);
        store_chunk<0>(s, qw + unit_of(qt, 0) + frag_offset(warp));
        store_chunk<1>(s, qw + unit_of(qt, 1) + frag_offset(warp));
        fence_async_smem();
        bar_sync(2 + wg, 256);
        wg_fence();
#pragma unroll
        for (int kk = 0; kk < 8; kk++) mma_ss<1>(o, (kk < 4 ? da0 : da1) + (kk & 3) * 2, (kk < 4 ? db0 : db1) + UNIT / 16 + (kk & 3) * 128, 1);
        wg_commit();
        mbar_wait(bfull, 0);
        wg_fence();
        issue_qk(s, qw + unit_of(qt, 0), qw + unit_of(qt, 1), base + unit_of(at, 0));
        wg_commit();
        bar_arrive(3 - wg, 256);
        wg_wait<1>();
        keep(o);
        mbar_arrive_cl(rempty, GE + 16);
        mbar_arrive_cl(rempty, GE + 24);
        store_chunk<0>(o, qw + unit_of(qt, 2) + frag_offset(warp));
        store_chunk<1>(o, qw + unit_of(qt, 3) + frag_offset(warp));
        wg_wait<0>();
        keep(s);
        mbar_arrive_cl(rempty, 0);
      }
      PROF(4, tid == 0 && ps == 1, 61);
      float l0 = 0.f, l1 = 0.f;
      auto step = [&](auto odd_c, const int j, uint32_t (&pw)[32], uint32_t (&pr)[32]) {
        constexpr bool ODD = decltype(odd_c)::value;
        const bool first = !ODD && (j & 2) == 0, last = ODD && j == 7;
        const uint32_t ph = (j >> 1) & 1;
        float i0, i1, a0, a1;
        const bool so = !ODD && j == 4;
        if (so) { i0 = inv_quad_sum(l0); i1 = inv_quad_sum(l1); l0 = 0.f; l1 = 0.f; }
        bool redo = !ODD && (j | ps) == 0;
        while (true) {
          if (redo) {
            float m0 = fmaxf(s[0], s[1]), m1 = fmaxf(s[2], s[3]);
#pragma unroll
            for (int i = 1; i < 16; i++) { m0 = fmaxf(m0, fmaxf(s[4 * i], s[4 * i + 1])); m1 = fmaxf(m1, fmaxf(s[4 * i + 2], s[4 * i + 3])); }
            m0 = fmaxf(m0, __shfl_xor_sync(0xffffffffu, m0, 1)); m1 = fmaxf(m1, __shfl_xor_sync(0xffffffffu, m1, 1));
            m0 = fmaxf(m0, __shfl_xor_sync(0xffffffffu, m0, 2)); m1 = fmaxf(m1, __shfl_xor_sync(0xffffffffu, m1, 2));
            m0 *= SCL2; m1 *= SCL2;
            if (!first) {
              m0 = fmaxf(m0, f0); m1 = fmaxf(m1, f1);
              const float c0 = ex2(f0 - m0), c1 = ex2(f1 - m1);
              l0 *= c0; l1 *= c1;
              wg_wait<0>();
              keep(o);
#pragma unroll
              for (int i = 0; i < 16; i++) { o[4 * i] *= c0; o[4 * i + 1] *= c0; o[4 * i + 2] *= c1; o[4 * i + 3] *= c1; }
            }
            f0 = m0; f1 = m1;
          }
          float b0 = 0.f, b1 = 0.f;
          a0 = 0.f; a1 = 0.f;
#pragma unroll
          for (int i = 0; i < 16; i++) {
            const float e0 = ex2(fmaf(s[4 * i], SCL2, -f0)), e1 = ex2(fmaf(s[4 * i + 1], SCL2, -f0));
            const float e2 = ex2(fmaf(s[4 * i + 2], SCL2, -f1)), e3 = ex2(fmaf(s[4 * i + 3], SCL2, -f1));
            a0 += e0; b0 += e1; a1 += e2; b1 += e3;
            pw[2 * i] = pack_bf(e0, e1); pw[2 * i + 1] = pack_bf(e2, e3);
            if (i == VREL) {
#pragma unroll
              for (int k = 0; k < 2 * VREL + 2; k++) asm volatile("" : "+r"(pw[k])::"memory");
              mbar_wait(bar_mod, 0);
              wg_wait<0>();
              mbar_arrive_cl(rempty, ODD ? 16 : 0, !redo && (ODD || j));
#pragma unroll
              for (int k = 4 * VREL + 4; k < 64; k++) asm volatile("" : "+f"(s[k])::"memory");
            }
          }
          a0 += b0; a1 += b1;
          if (redo) break;
          redo = __any_sync(0xffffffffu, !(a0 + a1 < 0x1p70f));
          if (first) {
            uint32_t m0 = __ballot_sync(0xffffffffu, a0 > 0x1p-50f), m1 = __ballot_sync(0xffffffffu, a1 > 0x1p-50f);
            m0 |= m0 >> 1; m1 |= m1 >> 1; m0 |= m0 >> 2; m1 |= m1 >> 2;
            redo = redo || (m0 & m1 & 0x11111111u) != 0x11111111u;
          }
          if (!redo) break;
        }
        l0 += a0; l1 += a1;
        keep(pw);
        keep(o);
        if (so) store_chunk<0>(o, i0, i1, qw + unit_of(qt, 0) + frag_offset(warp));
        keep(o);
        if (ODD && !(j & 2)) { fence_async_smem(); mbar_arrive_pred(bar_ofull + wg * 8, j > 4); }
        mbar_wait(bfull + (ODD ? 24 : 8), ph);
        bar_sync(2 + wg, 256);
        if (!last) {
          const uint32_t qn = qt >> (j >= 3 ? 8 : 0);
          wg_fence();
          issue_qk(s, qw + unit_of(qn, 0), qw + unit_of(qn, 1), base + unit_of(at, ODD ? 3 : 1));
          wg_commit();
          mbar_wait(bfull + (ODD ? 0 : 16), ODD ? ph ^ 1 : ph);
        }
        if (so) { store_chunk<1>(o, i0, i1, qw + unit_of(qt, 1) + frag_offset(warp)); keep(o); }
        wg_fence();
        issue_pv(o, pw, base + unit_of(at, ODD ? (last ? 3 : 0) : 2), !first);
        wg_commit();
        bar_arrive(3 - wg, 256);
        wg_wait<1>();
        keep(s);
        mbar_arrive_cl(rempty, ODD ? 24 : 8, !last);
        PROF(4, tid == 0 && ps == 1, 51 + j);
      };
      uint32_t pa[32], pb[32];
#pragma unroll 1
      for (int j = 0; j < 8; j += 2) {
        step(std::false_type{}, j, pa, pb);
        step(std::true_type{}, j + 1, pb, pa);
      }
      {
        const float i0 = inv_quad_sum(l0), i1 = inv_quad_sum(l1);
        wg_wait<0>();
        keep(o);
        mbar_arrive_cl(rempty, 24);
        store_chunk<0>(o, i0, i1, qw + unit_of(qt, 2) + frag_offset(warp));
        store_chunk<1>(o, i0, i1, qw + unit_of(qt, 3) + frag_offset(warp));
        fence_async_smem();
        mbar_arrive(bar_ofull + 16 + wg * 8);
      }
      PROF(2, tid == 0, 10 + ps * 8);
    }

    const int ln = fresh_lane(), g = ln >> 2, tq = ln & 3, ct = warp * 32 + ln;
    const bool lane0 = ln == 0;
    const int lrow0 = warp * 16 + g;
    const int grow0 = rb * 128 + lrow0;
    const uint32_t res = base + OFF_RES, trow = res + wg * 8192 + frag_offset(warp);
    uint32_t xr[32];
    uint4 sv[4], own;
    uint32_t* sp[4];
#pragma unroll
    for (int k = 0; k < 4; k++) sp[k] = g_stats + ((((tq >> 1) * 4 + k) ^ cj) * SEQ + grow0 + (tq & 1) * 8) * 4;
    {
      const uint64_t da = make_desc(base + wg * 8192, 16, 1024), db = make_desc(base, 8192, 1024);
      constexpr int U = UNIT / 16;
#define HALF_STAGE(acc, xu, wu) _Pragma("unroll") for (int kk = 0; kk < 4; kk++) mma_ss<1>(acc, da + (xu) * U + kk * 2, db + (wu) * U + kk * 128, 1)
      PROF(10, ct == PT, 19); STAMP(0);
      cluster_arrive();
      mbar_wait(gfull, 1);
      mbar_wait(gfull + 8, 1);
      bar_sync(2 + wg, 256);
      wg_fence();
      HALF_STAGE(o, 7, 1);
      HALF_STAGE(o, 8, 3);
      wg_commit();
      STAMP(16);
      mbar_wait(gfull + 16, 1);
      STAMP(17);
      wg_fence();
      HALF_STAGE(o, 6, 11);
      wg_commit();
      bar_arrive(3 - wg, 256);
      mbar_wait(bar_par, 0);
      uint32_t* xo = g_xch + ((size_t)b * 8 * 256 + ct) * 4;
      const uint32_t* xi = g_xch + ((size_t)(b ^ 2) * 8 * 256 + ct) * 4;
      const uint32_t par1 = (~lds1(par + PAR_CONST + 4) & 1) << 16;
      uint32_t ga[16];
      uint4 bw[8];
#define LOAD_PAR _Pragma("unroll") for (int i = 0; i < 8; i++) {                                                               \
        ga[2 * i] = lds1(par + PAR_T2 + i * 128 + tq * 16 + 12); ga[2 * i + 1] = lds1(par + PAR_T2 + i * 128 + 64 + tq * 16 + 12); \
        bw[i] = lds4(par + PAR_T1 + i * 64 + tq * 16);                                                                          \
        if (!(g & 1)) { bw[i].x = 0x3f803f80u; bw[i].y = 0x3f803f80u; }                                                         \
      }
      if (PPOS == 0) LOAD_PAR
      wg_wait<1>();
      mbar_arrive_pred(bar_rel, lane0);
      wg_wait<0>();
      keep(o);
      mbar_arrive_pred(bar_ring, lane0);
      PROF(8, ct == PT, 20); STAMP(1);
#define SEND(i) st_b128(xo + (i) * 1024, (pack_bf(o[8 * (i)], o[8 * (i) + 1]) & ~0x10000u) | par1, pack_bf(o[8 * (i) + 2], o[8 * (i) + 3]), \
                        pack_bf(o[8 * (i) + 4], o[8 * (i) + 5]), pack_bf(o[8 * (i) + 6], o[8 * (i) + 7]))
#pragma unroll
      for (int i = 0; i < NS1; i++) SEND(i);
      PROF(8, ct == PT, 21); STAMP(2);
      bar_sync(2 + wg, 256);
      wg_fence();
      HALF_STAGE(s, 7, 0);
      HALF_STAGE(s, 8, 2);
      HALF_STAGE(s, 6, 10);
      wg_commit();
      bar_arrive(3 - wg, 256);
      STAMP(18);
      mbar_wait(gfull + 24, 1);
#pragma unroll
      for (int i = NS1; i < 8; i++) SEND(i);
      uint4 v[8];
#pragma unroll
      for (int i = 0; i < 4; i++) v[i] = ld_b128(xi + i * 1024);
      if (PPOS == 1) LOAD_PAR
      STAMP(19);
      mbar_wait(bar_xres, 0);
      wg_wait<0>();
      mbar_arrive_pred(bar_ring + 8, lane0);
      bar_sync(2 + wg, 256);
      STAMP(20);
#pragma unroll
      for (int i = 4; i < 8; i++) v[i] = ld_b128(xi + i * 1024);
      mbar_wait(bar_xres, 0);
      wg_fence();
      HALF_STAGE(s, 9, 4);
      wg_commit();
      mbar_wait(bar_rx, 0);
      wg_fence();
      HALF_STAGE(s, 1, 5);
      wg_commit();
      bar_arrive(3 - wg, 256);
      STAMP(21);
      wg_wait<0>();
      keep(s);
      mbar_arrive_pred(bar_ring + 16, lane0);
      PROF(10, ct == PT, 23); STAMP(4);
#pragma unroll
      for (int i = 0; i < 16; i += 2) ldmatrix4((trow ^ ((i & 7) << 4)) + (i >> 3) * 16384, xr[2 * i], xr[2 * i + 1], xr[2 * i + 2], xr[2 * i + 3]);
      if (PPOS == 2) LOAD_PAR
      uint32_t pk[32];
      pack_p(s, pk);
      keep(pk);
      {
        uint32_t n = 0, miss;
        do {
          miss = 0;
#pragma unroll
          for (int i = 0; i < 8; i++) miss |= v[i].x ^ par1;
          miss = __any_sync(0xffffffffu, miss & 0x10000u);
          if (miss) {
#pragma unroll
            for (int i = 0; i < 8; i++)
              asm volatile("{ .reg .pred p; .reg .b32 t; xor.b32 t, %0, %5; and.b32 t, t, 0x10000; setp.ne.u32 p, t, 0;\n"
                           "@p ld.relaxed.gpu.global.v4.u32 {%0, %1, %2, %3}, [%4]; }"
                           : "+r"(v[i].x), "+r"(v[i].y), "+r"(v[i].z), "+r"(v[i].w) : "l"(xi + i * 1024), "r"(par1) : "memory");
          }
          watchdog(n);
        } while (miss);
      }
      PROF(8, ct == PT, 22); STAMP(3);
#pragma unroll
      for (int k = 0; k < 4; k++) sv[k] = ESV ? ld_b128(sp[k]) : make_uint4(0, 0, 0, 0);
      float ds[4] = {0.f, 0.f, 0.f, 0.f}, dl[4] = {0.f, 0.f, 0.f, 0.f}, q0[4] = {0.f, 0.f, 0.f, 0.f}, q1[4] = {0.f, 0.f, 0.f, 0.f};
#pragma unroll
      for (int i = 0; i < 8; i++) {
        const uint32_t u0 = hfma2(ga[2 * i], hadd2(pk[4 * i], v[i].x & ~0x10000u), xr[4 * i]);
        const uint32_t u1 = hfma2(ga[2 * i], hadd2(pk[4 * i + 1], v[i].y), xr[4 * i + 1]);
        const uint32_t u2 = hfma2(ga[2 * i + 1], hadd2(pk[4 * i + 2], v[i].z), xr[4 * i + 2]);
        const uint32_t u3 = hfma2(ga[2 * i + 1], hadd2(pk[4 * i + 3], v[i].w), xr[4 * i + 3]);
        xr[4 * i] = u0; xr[4 * i + 1] = u1; xr[4 * i + 2] = u2; xr[4 * i + 3] = u3;
        mma16816(ds, u0, u1, u2, u3, bw[i].x, bw[i].y);
        mma16816(dl, u0, u1, u2, u3, bw[i].z, bw[i].w);
        mma16816(q0, u0, u1, u2, u3, u0, u2);
        mma16816(q1, u0, u1, u2, u3, u1, u3);
      }
      const float sqa = __shfl_sync(0xffffffffu, (g & 1) ? q0[1] : q0[0], g * 4 + (g >> 1));
      const float sqb = __shfl_sync(0xffffffffu, (g & 1) ? q1[3] : q1[2], g * 4 + (g >> 1));
      own = (tq & 1) ? make_uint4(__float_as_uint(ds[2]), __float_as_uint(sqb), __float_as_uint(ds[3] + dl[3]), tag)
                                 : make_uint4(__float_as_uint(ds[0]), __float_as_uint(sqa), __float_as_uint(ds[1] + dl[1]), tag);
      if (tq < 2) st_b128(sp[0], own.x, own.y, own.z, own.w);
    }
    PROF(8, ct == PT, 29); STAMP(5);
    uint32_t mm, ih, il;
    float rbest;
    uint32_t wf[128];
    const uint32_t frow = (ln & 7) + (ln >> 4) * 8;
    const uint32_t wfo = base + (warp & 1) * 8192 + frow * 64 + ((((ln >> 3) & 1) ^ ((frow >> 1) & 3)) << 4);
#define LOAD_WF(m) _Pragma("unroll") for (int f = 0; f < 16; f++) {                                                   \
      const int r = ((f >> 1) * 4 + (m) * 2 + (f & 1)) * 4;                                                           \
      ldmatrix4t(((wfo + unit_of((m) ? FT_U : FT_G, warp >> 1)) ^ ((f & 1) * 32)) + (f >> 1) * 1024, wf[r], wf[r + 1], wf[r + 2], wf[r + 3]); \
    }
    bool early, wait1;
    {
#pragma unroll
      for (int i = 0; i < 16; i += 2) stmatrix4((trow ^ ((i & 7) << 4)) + (i >> 3) * 16384, xr[2 * i], xr[2 * i + 1], xr[2 * i + 2], xr[2 * i + 3]);
      const uint4 cst = lds4(par + PAR_CONST);
      const float A1 = __uint_as_float(cst.x), A2 = __uint_as_float(cst.z);
      uint32_t n = 0;
      early = false; wait1 = false;
#pragma unroll 1
      while (true) {
        uint32_t miss;
        asm volatile("{ .reg .pred p0, p1, p2, p3; .reg .b64 u, v; .reg .b128 w;\n"
                     "setp.ge.u32 p0, %22, 2; setp.ne.and.u32 p0, %4, %21, p0; setp.ne.u32 p1, %8, %21; setp.ne.u32 p2, %12, %21; setp.ne.u32 p3, %16, %21;\n"
                     "@p0 ld.relaxed.gpu.global.v4.u32 {%1, %2, %3, %4}, [%17];\n"
                     "@p1 ld.relaxed.gpu.global.v4.u32 {%5, %6, %7, %8}, [%18];\n"
                     "@p2 ld.relaxed.gpu.global.v4.u32 {%9, %10, %11, %12}, [%19];\n"
                     "@p3 ld.relaxed.gpu.global.v4.u32 {%13, %14, %15, %16}, [%20];\n"
                     "or.pred p0, p0, p1; or.pred p2, p2, p3; or.pred p0, p0, p2; vote.sync.any.pred p0, p0, 0xffffffff; selp.u32 %0, 1, 0, p0; }"
                     : "=r"(miss), "+r"(sv[0].x), "+r"(sv[0].y), "+r"(sv[0].z), "+r"(sv[0].w), "+r"(sv[1].x), "+r"(sv[1].y), "+r"(sv[1].z), "+r"(sv[1].w),
                       "+r"(sv[2].x), "+r"(sv[2].y), "+r"(sv[2].z), "+r"(sv[2].w), "+r"(sv[3].x), "+r"(sv[3].y), "+r"(sv[3].z), "+r"(sv[3].w)
                     : "l"(sp[0]), "l"(sp[1]), "l"(sp[2]), "l"(sp[3]), "r"(tag), "r"(tq) : "memory");
        if (!miss) break;
        wait1 = true;
        if (!early && (b >= NFFN || __all_sync(0xffffffffu, mbar_test(bar_box + (warp >> 1) * 8, 0)))) {
          early = true;
          LOAD_WF(0);
          __syncwarp();
          mbar_arrive_pred(bar_gate, lane0);
        }
        watchdog(n);
      }
      const uint4 v0 = tq < 2 ? own : sv[0], v1 = sv[1], v2 = sv[2], v3 = sv[3];
      PROF(8, ct == PT, 30); STAMP(6);
      float su = (__uint_as_float(v0.x) + __uint_as_float(v1.x)) + (__uint_as_float(v2.x) + __uint_as_float(v3.x));
      float sq = (__uint_as_float(v0.y) + __uint_as_float(v1.y)) + (__uint_as_float(v2.y) + __uint_as_float(v3.y));
      float dt = (__uint_as_float(v0.z) + __uint_as_float(v1.z)) + (__uint_as_float(v2.z) + __uint_as_float(v3.z));
      su += __shfl_xor_sync(0xffffffffu, su, 2); sq += __shfl_xor_sync(0xffffffffu, sq, 2); dt += __shfl_xor_sync(0xffffffffu, dt, 2);
      const float m = su * (1.f / DM);
      float mb, sd;
      ln_scalars(m, fmaxf(sq * (1.f / DM) - m * m, 0.f), mb, sd);
      const float inv = rcp(sd);
      rbest = (dt - mb * A1) * inv + A2;
      mm = pack_bf(mb, mb);
      ih = pack_bf(inv, inv);
      const float lo = inv - bf_lo(ih);
      il = pack_bf(lo, lo);
    }
    int ibest;
    {
      const uint32_t bits = __float_as_uint(rbest);
      const uint32_t key = (((int)bits < 0 ? ~bits : bits | 0x80000000u) & ~0x1ffu) | ((127 - lrow0 - (tq & 1) * 8) << 2) | tag;
      sts1(par + PAR_RED + warp * 4, __reduce_max_sync(0xffffffffu, key));
      PROF(8, ct == PT, 38); STAMP(7);
      uint32_t waited;
      asm volatile("{ .reg .pred p, q; setp.ne.u32 p, %1, 0; barrier.cta.red.or.pred q, 1, 256, p; selp.u32 %0, 1, 0, q; }" : "=r"(waited) : "r"((uint32_t)(wait1 && (wg || CW0))) : "memory");
      const uint4 ka = lds4(par + PAR_RED), kb = lds4(par + PAR_RED + 16);
      const uint32_t k2 = max(max(max(ka.x, ka.y), max(ka.z, ka.w)), max(max(kb.x, kb.y), max(kb.z, kb.w)));
      if (ct == 0 && ((cj & CWM) == 0 || (CWL && !waited))) st_relaxed(g_cand + rb, k2);
      ibest = 127 - ((k2 >> 2) & 127);
    }
    PROF(8, ct == PT, 39); STAMP(8);
    if ((ibest >> 4) == warp) {
      const int src = (ibest & 7) * 4 + ((ibest >> 3) & 1), ch = g * 2;
      const uint32_t cm = __shfl_sync(0xffffffffu, mm, src), ch_ = __shfl_sync(0xffffffffu, ih, src), cl = __shfl_sync(0xffffffffu, il, src);
      const uint32_t xa = res + (ch >> 3) * 16384 + ibest * 128 + (((ch & 7) ^ (ibest & 7)) << 4) + tq * 4;
      const uint32_t x0 = lds1(xa), x1 = lds1(xa ^ 16);
      const uint2 p0 = lds2(par + PAR_T2 + ch * 64 + tq * 16), p1 = lds2(par + PAR_T2 + ch * 64 + 64 + tq * 16);
      uint32_t* dst = g_row + rb * 2 * DM + cj * 128 + ln * 4;
      st_pairs(dst, ln_mod(x0, cm, ch_, cl, p0.x, p0.y), ln_mod(x1, cm, ch_, cl, p1.x, p1.y), tag);
      st_pairs(dst + DM, x0, x1, tag);
      __syncwarp();
    }
    PROF(8, ct == PT, 37); STAMP(9);
    uint32_t wd[64];
    const uint32_t wda = base + unit_of(FT_D, warp >> 1) + (warp & 1) * 8192 + frow * 128 + ((((ln >> 3) & 1) ^ (ln & 7)) << 4);
#define LOAD_WD(f) ldmatrix4t((wda ^ ((((f) >> 1) & 3) * 32)) + ((f) >> 3) * 4096 + ((f) & 1) * 2048, wd[4 * (f)], wd[4 * (f) + 1], wd[4 * (f) + 2], wd[4 * (f) + 3])
    if (!early) {
      if (b < NFFN) mbar_wait(bar_box + (warp >> 1) * 8, 0);
      LOAD_WF(0);
      __syncwarp();
      mbar_arrive_pred(bar_gate, lane0);
    }
    if (b < NFFN) {
      const uint32_t own = base + unit_of(FT_G, warp >> 1) + (warp & 1) * 8192;
      mbar_wait(bar_box + (4 + (warp >> 1)) * 8, 0);
      LOAD_WF(1);
      uint32_t* const ydst = g_ypart + ((size_t)(warp * 16 + tq * 2) * NFFN + b) * 8 + g;
      PROF(8, ct == PT, 31); STAMP(10);
      mbar_wait(bar_box + (8 + (warp >> 1)) * 8, 0);
#pragma unroll
      for (int f = 0; f < WDE; f++) LOAD_WD(f);
      STAMP(11);
      mbar_wait(bar_sel, 0);
      PROF(8, ct == PT, 33); STAMP(12);
      float d[8][4];
#pragma unroll
      for (int i = 0; i < 4; i++) { d[i][0] = 0.f; d[i][1] = 0.f; d[i][2] = 0.f; d[i][3] = 0.f; }
#pragma unroll
      for (int ks = 0; ks < 8; ks++) {
        const uint2 hb = lds2(own + 256 + ks * 32 + tq * 8);
#pragma unroll
        for (int mt = 0; mt < 4; mt++) {
          const int r = ks * 16 + mt * 4;
          mma16816(d[mt], wf[r], wf[r + 1], wf[r + 2], wf[r + 3], hb.x, hb.y);
        }
      }
      sts2(own + (tq * 8 + g) * 8, __float_as_uint((tq & 2) ? ((tq & 1) ? d[1][2] : d[1][0]) : ((tq & 1) ? d[0][2] : d[0][0])),
           __float_as_uint((tq & 2) ? ((tq & 1) ? d[3][2] : d[3][0]) : ((tq & 1) ? d[2][2] : d[2][0])));
      bar_sync(1, 256);
      uint32_t ab[4];
      {
        float G = 0.f, U = 0.f;
        uint2 pv[8];
#pragma unroll
        for (int w8 = 0; w8 < 8; w8++) pv[w8] = lds2(base + ln * 8 + ((FT_G >> (w8 >> 1) * 4) & 15) * UNIT + (w8 & 1) * 8192);
#pragma unroll
        for (int w8 = 0; w8 < 8; w8 += 2) {
          G += __uint_as_float(pv[w8].x) + __uint_as_float(pv[w8 + 1].x);
          U += __uint_as_float(pv[w8].y) + __uint_as_float(pv[w8 + 1].y);
        }
#pragma unroll
        for (int f = WDE; f < 16; f++) LOAD_WD(f);
        const float act = rbf(silu_f(rbf(G))) * rbf(U);
        const uint32_t pk = pack_bf(act, __shfl_down_sync(0xffffffffu, act, 1));
#pragma unroll
        for (int i = 0; i < 4; i++) ab[i] = __shfl_sync(0xffffffffu, pk, i * 8 + tq * 2);
      }
      PROF(8, ct == PT, 34); STAMP(13);
#pragma unroll
      for (int mt = 0; mt < 8; mt++) {
        d[mt][0] = 0.f; d[mt][1] = 0.f; d[mt][2] = 0.f; d[mt][3] = 0.f;
        mma16816(d[mt], wd[mt * 8], wd[mt * 8 + 1], wd[mt * 8 + 2], wd[mt * 8 + 3], ab[0], ab[1]);
        mma16816(d[mt], wd[mt * 8 + 4], wd[mt * 8 + 5], wd[mt * 8 + 6], wd[mt * 8 + 7], ab[2], ab[3]);
      }
#pragma unroll
      for (int i = 0; i < 4; i++) {
        const int m4 = (i >> 1) * 4, e = (i & 1) * 2;
        const float y = (tq & 2) ? ((tq & 1) ? d[m4 + 3][e] : d[m4 + 2][e]) : ((tq & 1) ? d[m4 + 1][e] : d[m4][e]);
        st_relaxed(ydst + (m4 * 2 + (i & 1)) * NFFN * 8, tagf(y, tag));
      }
      PROF(8, ct == PT, 35); STAMP(14);
    }
    mbar_wait(bar_sel, 0);
    mbar_arrive_pred(bar_win, ct == 0);
    const int iwin = lds1(par + PAR_CONST + 60) & 0x7ff;
    const bool cand = (iwin >> 4) == rb * 8 + warp;
    {
      const uint32_t mm0 = __shfl_sync(0xffffffffu, mm, ln & ~1), mm1 = __shfl_sync(0xffffffffu, mm, ln | 1);
      const uint32_t ih0 = __shfl_sync(0xffffffffu, ih, ln & ~1), ih1 = __shfl_sync(0xffffffffu, ih, ln | 1);
      const uint32_t il0 = __shfl_sync(0xffffffffu, il, ln & ~1), il1 = __shfl_sync(0xffffffffu, il, ln | 1);
#pragma unroll 1
      for (int hf = 0; hf < 2; hf++) {
        uint32_t x[16];
#pragma unroll
        for (int i = 0; i < 8; i += 2) ldmatrix4((trow ^ (i << 4)) + hf * 16384, x[2 * i], x[2 * i + 1], x[2 * i + 2], x[2 * i + 3]);
#pragma unroll
        for (int i = 0; i < 8; i++) {
          const uint4 pv = lds4(par + PAR_T2 + (hf * 8 + i) * 64 + tq * 16);
          x[2 * i] = hadd2(x[2 * i], hmul2(pv.z, ln_mod(x[2 * i], mm0, ih0, il0, pv.x, pv.y)));
          x[2 * i + 1] = hadd2(x[2 * i + 1], hmul2(pv.z, ln_mod(x[2 * i + 1], mm1, ih1, il1, pv.x, pv.y)));
        }
#pragma unroll
        for (int i = 0; i < 8; i += 2) stmatrix4((trow ^ (i << 4)) + hf * 16384, x[2 * i], x[2 * i + 1], x[2 * i + 2], x[2 * i + 3]);
      }
      if (!cand) fence_async_smem();
      __syncwarp();
      if (!cand && elect_one()) {
        tma2d_store(&maps.out, res + warp * 2048, cj * 128, rb * 128 + warp * 16);
        tma2d_store(&maps.out, res + 16384 + warp * 2048, cj * 128 + 64, rb * 128 + warp * 16);
        asm volatile("cp.async.bulk.commit_group;" ::: "memory");
      }
    }
    if (cand) {
      const int wrow0 = warp * 16;
#pragma unroll 2
      for (int p = 0; p < 8; p++) {
        const int row = 2 * p + (ln >> 4), ch = ln & 15;
        const uint4 v = lds4(res + (ch >> 3) * 16384 + (wrow0 + row) * 128 + (((ch & 7) ^ (row & 7)) << 4));
        if (rb * 128 + wrow0 + row != iwin) *reinterpret_cast<uint4*>(P.out + (size_t)(rb * 128 + wrow0 + row) * DM + cj * 128 + ch * 8) = v;
      }
    }
    asm volatile("cp.async.bulk.wait_group.read 0;" ::: "memory");
    PROF(8, ct == PT, 11); STAMP(15);
    cluster_wait();
  }
}

typedef CUresult (*EncodeFn)(CUtensorMap*, CUtensorMapDataType, cuuint32_t, void*, const cuuint64_t*, const cuuint64_t*,
                             const cuuint32_t*, const cuuint32_t*, CUtensorMapInterleave, CUtensorMapSwizzle,
                             CUtensorMapL2promotion, CUtensorMapFloatOOBfill);

void map2d(EncodeFn enc, CUtensorMap* m, const void* p, uint64_t rows, uint64_t cols, uint32_t brows) {
  cuuint64_t dims[2] = {cols, rows}, strides[1] = {cols * 2};
  cuuint32_t box[2] = {64, brows}, es[2] = {1, 1};
  enc(m, CU_TENSOR_MAP_DATA_TYPE_BFLOAT16, 2, const_cast<void*>(p), dims, strides, box, es, CU_TENSOR_MAP_INTERLEAVE_NONE,
      CU_TENSOR_MAP_SWIZZLE_128B, CU_TENSOR_MAP_L2_PROMOTION_L2_256B, CU_TENSOR_MAP_FLOAT_OOB_FILL_NONE);
}
void map2d_narrow(EncodeFn enc, CUtensorMap* m, const void* p, uint64_t rows, uint64_t cols, uint32_t brows) {
  cuuint64_t dims[2] = {cols, rows}, strides[1] = {cols * 2};
  cuuint32_t box[2] = {32, brows}, es[2] = {1, 1};
  enc(m, CU_TENSOR_MAP_DATA_TYPE_BFLOAT16, 2, const_cast<void*>(p), dims, strides, box, es, CU_TENSOR_MAP_INTERLEAVE_NONE,
      CU_TENSOR_MAP_SWIZZLE_64B, CU_TENSOR_MAP_L2_PROMOTION_L2_64B, CU_TENSOR_MAP_FLOAT_OOB_FILL_NONE);
}
void map3d(EncodeFn enc, CUtensorMap* m, const void* p, uint64_t rows, uint64_t cols, uint32_t brows, uint32_t nch) {
  cuuint64_t dims[3] = {64, rows, cols / 64}, strides[2] = {cols * 2, 128};
  cuuint32_t box[3] = {64, brows, nch}, es[3] = {1, 1, 1};
  enc(m, CU_TENSOR_MAP_DATA_TYPE_BFLOAT16, 3, const_cast<void*>(p), dims, strides, box, es, CU_TENSOR_MAP_INTERLEAVE_NONE,
      CU_TENSOR_MAP_SWIZZLE_128B, CU_TENSOR_MAP_L2_PROMOTION_L2_256B, CU_TENSOR_MAP_FLOAT_OOB_FILL_NONE);
}

}

extern "C" void kernel_launch(void* const* d_in, const int* in_sizes, int n_in, void* d_out, int out_size) {
  (void)in_sizes; (void)n_in; (void)out_size;
  static EncodeFn enc = nullptr;
  if (!enc) {
    void* fn = nullptr;
    cudaDriverEntryPointQueryResult st;
    cudaGetDriverEntryPoint("cuTensorMapEncodeTiled", &fn, cudaEnableDefault, &st);
    enc = (EncodeFn)fn;
    cudaFuncSetAttribute(fused_kernel, cudaFuncAttributeMaxDynamicSharedMemorySize, SMEM_BYTES);
  }
  Maps maps;
  map2d(enc, &maps.x, d_in[0], SEQ, DM, 128);
  map2d(enc, &maps.out, d_out, SEQ, DM, 16);
  map3d(enc, &maps.wq, d_in[3], DM, NQ, 64, 2);
  map3d(enc, &maps.k, d_in[1], 4 * SK, 128, 128, 1);
  map3d(enc, &maps.v, d_in[2], 4 * SK, 128, 128, 1);
  map3d(enc, &maps.wo, d_in[4], NQ, DM, 64, 2);
  map2d_narrow(enc, &maps.wg, d_in[7], DM, FF, 256);
  map2d_narrow(enc, &maps.wu, d_in[8], DM, FF, 256);
  map3d(enc, &maps.wd, d_in[9], FF, DM, 32, 4);
  map2d_narrow(enc, &maps.wm, d_in[11], DM, NMOD, 256);
  Ptrs p;
  p.x = (const __nv_bfloat16*)d_in[0];
  p.w_r = (const __nv_bfloat16*)d_in[6];
  p.w_gate = (const __nv_bfloat16*)d_in[7];
  p.w_up = (const __nv_bfloat16*)d_in[8];
  p.w_down = (const __nv_bfloat16*)d_in[9];
  p.c = (const __nv_bfloat16*)d_in[10];
  p.w_mod = (const __nv_bfloat16*)d_in[11];
  p.out = (__nv_bfloat16*)d_out;
  fused_kernel<<<NMAIN + NHELP, 384, SMEM_BYTES>>>(maps, p);
}
```

```cpp
#include <cuda_runtime.h>
#include <cuda_bf16.h>
#include <cuda.h>
#include <stdint.h>
#include <type_traits>

#define HD 2
#define HDX 2
#define NRS 8
#define FPACE 3
#define GOST 20
#define WB 2
#define WN 20
#define RES0 17
#define RES1 20
#define HU 32
#define NS1 6
#define PG0 15
#define PSL 0
#define CWM 7
#define WDE 16
#define CWL 1
#define CW0 0
#define ESV 1
#define PPOS 1
#define FB0 0
#define FB2 8
#define OPS 8192
#define OFL 0
#define ODS 8
#define MODUL hfma2
#define ODS1 5
#define HPS 8192
#define VREL 5
#define E0 3

namespace {

constexpr int SEQ = 2048, DM = 1024, NQ = 4096, SK = 2048, WIN = 512, FF = 3584, NMOD = 6144;
constexpr int NMAIN = 128, NHELP = 4, NFFN = 112;
constexpr int NSLOT = 4, SLOT_BYTES = 32768, UNIT = 16384, GST_BYTES = 3 * UNIT;
constexpr uint32_t XT1 = 0xDCBA, XT2 = 0x9687;
constexpr uint32_t WT0 = 0xA741, WT1 = 0x7420, WT2 = 0x4A20;
constexpr uint32_t AT0 = WT1, AT1 = WT2;
constexpr uint32_t QT = 0xDC9696DC;
constexpr int OFF_STAGE = 12 * UNIT;
constexpr uint32_t FT_G = 0x07B3, FT_U = 0xA628, FT_D = 0x5149;
constexpr int OFF_RES = 12 * UNIT;
constexpr int OFF_PAR = 14 * UNIT;
constexpr int OFF_BAR = OFF_PAR + 2528;
constexpr int SMEM_BYTES = OFF_BAR + 544;
static_assert(SMEM_BYTES <= 232448, "smem");

constexpr int PAR_T1 = 0;
constexpr int PAR_T2 = 512;
constexpr int PAR_CONST = 1536;
constexpr int PAR_RED = 1600;
constexpr int PAR_SINK = 2176;

struct Maps {
  CUtensorMap x, wq, k, v, wo, wg, wu, wd, wm, out;
};
struct Ptrs {
  const __nv_bfloat16 *x, *w_r, *c, *w_mod, *w_gate, *w_up, *w_down;
  __nv_bfloat16* out;
};

__device__ __align__(1024) uint8_t g_act[16 * 80 * UNIT];
__device__ __align__(128) uint32_t g_mod[NMOD];
__device__ __align__(128) uint32_t g_modp[2 * 2 * DM];
__device__ __align__(128) uint32_t g_ln1[SEQ * 4];
__device__ __align__(128) uint32_t g_cnt_h[16 * 32];
__device__ __align__(128) uint32_t g_cnt_o[128 * 32];
__device__ __align__(128) uint32_t g_xch[NMAIN * 8 * 256 * 4];
__device__ __align__(128) uint32_t g_stats[8 * SEQ * 4];
__device__ __align__(128) uint32_t g_cand[32];
__device__ __align__(128) uint32_t g_row[16 * 2 * DM];
__device__ __align__(128) uint32_t g_ypart[NMAIN * NFFN * 8];
__device__ uint32_t g_epoch;

__device__ __forceinline__ uint32_t fresh_lane() { uint32_t l; asm volatile("mov.u32 %0, %%laneid;" : "=r"(l)); return l; }
__device__ __forceinline__ uint32_t frag_offset(int warp) {
  const uint32_t l = fresh_lane();
  return ((warp & 3) * 16 + (l & 15)) * 128 + (((l >> 4) ^ (l & 7)) << 4);
}
__device__ __forceinline__ bool elect_one() {
  uint32_t p;
  asm volatile("{ .reg .pred q; elect.sync _|q, 0xffffffff; selp.u32 %0, 1, 0, q; }" : "=r"(p));
  return p;
}
__device__ __forceinline__ uint32_t smem_u32(const void* p) { return (uint32_t)__cvta_generic_to_shared(p); }
__device__ __forceinline__ void mbar_init(uint32_t bar, uint32_t cnt) {
  asm volatile("mbarrier.init.shared::cta.b64 [%0], %1;" ::"r"(bar), "r"(cnt) : "memory");
}
__device__ __forceinline__ void mbar_expect_tx(uint32_t bar, uint32_t bytes) {
  asm volatile("mbarrier.arrive.expect_tx.shared::cta.b64 _, [%0], %1;" ::"r"(bar), "r"(bytes) : "memory");
}
__device__ __forceinline__ void mbar_arrive(uint32_t bar) {
  asm volatile("mbarrier.arrive.shared::cta.b64 _, [%0];" ::"r"(bar) : "memory");
}
__device__ __forceinline__ void mbar_arrive_pred(uint32_t bar, bool p) {
  asm volatile("{ .reg .pred p; setp.ne.b32 p, %1, 0; @p mbarrier.arrive.shared::cta.b64 _, [%0]; }" ::"r"(bar), "r"((int)p) : "memory");
}
__device__ __forceinline__ void mbar_arrive_cl(uint32_t bar, uint32_t off, bool p = true) {
  asm volatile("{ .reg .pred p, q; .reg .b32 a; setp.ne.b32 q, %2, 0; setp.ne.and.b32 p, %0, 0, q; add.u32 a, %0, %1; @p mbarrier.arrive.shared::cluster.b64 _, [a]; }"
               ::"r"(bar), "r"(off), "r"((int)p) : "memory");
}
__device__ __forceinline__ uint32_t mapa(uint32_t addr, uint32_t cta) {
  uint32_t r; asm("mapa.shared::cluster.u32 %0, %1, %2;" : "=r"(r) : "r"(addr), "r"(cta)); return r;
}
__device__ __forceinline__ void cluster_arrive() { asm volatile("barrier.cluster.arrive.relaxed.aligned;" ::: "memory"); }
__device__ __forceinline__ void cluster_wait() { asm volatile("barrier.cluster.wait.aligned;" ::: "memory"); }
__device__ __forceinline__ void watchdog(uint32_t& n) {
}
__device__ __forceinline__ void mbar_wait(uint32_t bar, uint32_t parity) {
  asm volatile("{\n.reg .pred p;\nWAIT_%=:\nmbarrier.try_wait.parity.shared::cta.b64 p, [%0], %1;\n@!p bra WAIT_%=;\n}" ::"r"(bar), "r"(parity) : "memory");
}
__device__ __forceinline__ bool mbar_test(uint32_t bar, uint32_t parity) {
  uint32_t ok;
  asm volatile("{\n.reg .pred p;\nmbarrier.test_wait.parity.shared::cta.b64 p, [%1], %2;\nselp.u32 %0, 1, 0, p;\n}" : "=r"(ok) : "r"(bar), "r"(parity) : "memory");
  return ok;
}
__device__ __forceinline__ uint64_t l2_stream() {
  uint64_t f; asm("createpolicy.fractional.L2::evict_first.b64 %0, 1.0;" : "=l"(f)); return f;
}
__device__ __forceinline__ void tma2d(uint32_t dst, const CUtensorMap* m, int c0, int c1, uint32_t bar) {
  asm volatile("cp.async.bulk.tensor.2d.shared::cluster.global.mbarrier::complete_tx::bytes.L2::cache_hint [%0], [%1, {%3, %4}], [%2], %5;"
               ::"r"(dst), "l"(m), "r"(bar), "r"(c0), "r"(c1), "l"(l2_stream()) : "memory");
}
__device__ __forceinline__ void bulk_load(uint32_t dst, const void* src, uint32_t bytes, uint32_t bar) {
  asm volatile("cp.async.bulk.shared::cluster.global.mbarrier::complete_tx::bytes [%0], [%1], %2, [%3];" ::"r"(dst), "l"(src), "r"(bytes), "r"(bar) : "memory");
}
__device__ __forceinline__ void bulk_load_stream(uint32_t dst, const void* src, uint32_t bytes, uint32_t bar) {
  asm volatile("cp.async.bulk.shared::cluster.global.mbarrier::complete_tx::bytes.L2::cache_hint [%0], [%1], %2, [%3], %4;"
               ::"r"(dst), "l"(src), "r"(bytes), "r"(bar), "l"(l2_stream()) : "memory");
}
__device__ __forceinline__ void tma2d_store(const CUtensorMap* m, uint32_t src, int c0, int c1) {
  asm volatile("cp.async.bulk.tensor.2d.global.shared::cta.bulk_group [%0, {%2, %3}], [%1];" ::"l"(m), "r"(src), "r"(c0), "r"(c1) : "memory");
}
__device__ __forceinline__ void bulk_store(void* dst, uint32_t src, uint32_t bytes) {
  asm volatile("cp.async.bulk.global.shared::cta.bulk_group [%0], [%1], %2;" ::"l"(dst), "r"(src), "r"(bytes) : "memory");
}
__device__ __forceinline__ uint32_t unit_of(uint32_t table, uint32_t i) { return ((table >> (i * 4)) & 15) * UNIT; }
__device__ __forceinline__ void tma3d(uint32_t dst, const CUtensorMap* m, int c0, int c1, int c2, uint32_t bar) {
  asm volatile("cp.async.bulk.tensor.3d.shared::cluster.global.mbarrier::complete_tx::bytes.L2::cache_hint [%0], [%1, {%3, %4, %5}], [%2], %6;"
               ::"r"(dst), "l"(m), "r"(bar), "r"(c0), "r"(c1), "r"(c2), "l"(l2_stream()) : "memory");
}
template <bool STREAM>
__device__ __forceinline__ void tma3d_mc(uint32_t dst, const CUtensorMap* m, int c0, int c1, int c2, uint32_t bar) {
  if (STREAM)
    asm volatile("cp.async.bulk.tensor.3d.shared::cluster.global.mbarrier::complete_tx::bytes.multicast::cluster.L2::cache_hint [%0], [%1, {%3, %4, %5}], [%2], %6, %7;"
                 ::"r"(dst), "l"(m), "r"(bar), "r"(c0), "r"(c1), "r"(c2), "h"((uint16_t)3), "l"(l2_stream()) : "memory");
  else
    asm volatile("cp.async.bulk.tensor.3d.shared::cluster.global.mbarrier::complete_tx::bytes.multicast::cluster [%0], [%1, {%3, %4, %5}], [%2], %6;"
                 ::"r"(dst), "l"(m), "r"(bar), "r"(c0), "r"(c1), "r"(c2), "h"((uint16_t)3) : "memory");
}
__device__ __forceinline__ void prefetch_map(const CUtensorMap* m) {
  asm volatile("prefetch.tensormap [%0];" ::"l"(m) : "memory");
}
__device__ __forceinline__ void fence_async() { asm volatile("fence.proxy.async.global;" ::: "memory"); }
__device__ __forceinline__ void fence_async_smem() { asm volatile("fence.proxy.async.shared::cta;" ::: "memory"); }
__device__ __forceinline__ void bar_sync(int id, int n) { asm volatile("bar.sync %0, %1;" ::"r"(id), "r"(n) : "memory"); }
__device__ __forceinline__ void bar_arrive(int id, int n) { asm volatile("bar.arrive %0, %1;" ::"r"(id), "r"(n) : "memory"); }
__device__ __forceinline__ void wg_fence() { asm volatile("wgmma.fence.sync.aligned;" ::: "memory"); }
__device__ __forceinline__ void wg_commit() { asm volatile("wgmma.commit_group.sync.aligned;" ::: "memory"); }
template <int N> __device__ __forceinline__ void wg_wait() { asm volatile("wgmma.wait_group.sync.aligned %0;" ::"n"(N) : "memory"); }
__device__ __forceinline__ uint64_t make_desc(uint32_t addr, uint32_t lbo, uint32_t sbo) {
  return (uint64_t)((addr & 0x3FFFF) >> 4) | ((uint64_t)(lbo >> 4) << 16) | ((uint64_t)(sbo >> 4) << 32) | (1ull << 62);
}
__device__ __forceinline__ uint32_t ld_relaxed(const uint32_t* p) {
  uint32_t v; asm volatile("ld.relaxed.gpu.global.u32 %0, [%1];" : "=r"(v) : "l"(p) : "memory"); return v;
}
__device__ __forceinline__ uint32_t ld_acquire(const uint32_t* p) {
  uint32_t v; asm volatile("ld.acquire.gpu.global.u32 %0, [%1];" : "=r"(v) : "l"(p) : "memory"); return v;
}
__device__ __forceinline__ uint4 ld_relaxed4(const uint32_t* p) {
  uint4 v; asm volatile("ld.relaxed.gpu.global.v4.u32 {%0,%1,%2,%3}, [%4];" : "=r"(v.x), "=r"(v.y), "=r"(v.z), "=r"(v.w) : "l"(p) : "memory"); return v;
}
__device__ __forceinline__ uint2 ld_relaxed2(const uint32_t* p) {
  uint2 v; asm volatile("ld.relaxed.gpu.global.v2.u32 {%0,%1}, [%2];" : "=r"(v.x), "=r"(v.y) : "l"(p) : "memory"); return v;
}
__device__ __forceinline__ void st_relaxed(uint32_t* p, uint32_t v) {
  asm volatile("st.relaxed.gpu.global.u32 [%0], %1;" ::"l"(p), "r"(v) : "memory");
}
__device__ __forceinline__ void st_relaxed2(uint32_t* p, uint32_t a, uint32_t b) {
  asm volatile("st.relaxed.gpu.global.v2.u32 [%0], {%1,%2};" ::"l"(p), "r"(a), "r"(b) : "memory");
}
__device__ __forceinline__ void st_relaxed4(uint32_t* p, uint32_t a, uint32_t b, uint32_t c, uint32_t d) {
  asm volatile("st.relaxed.gpu.global.v4.u32 [%0], {%1,%2,%3,%4};" ::"l"(p), "r"(a), "r"(b), "r"(c), "r"(d) : "memory");
}
__device__ __forceinline__ void st_b128(uint32_t* p, uint32_t a, uint32_t b, uint32_t c, uint32_t d) {
  asm volatile("{ .reg .b64 u, v; .reg .b128 w; mov.b64 u, {%1, %2}; mov.b64 v, {%3, %4}; mov.b128 w, {u, v}; st.relaxed.gpu.global.b128 [%0], w; }"
               ::"l"(p), "r"(a), "r"(b), "r"(c), "r"(d) : "memory");
}
__device__ __forceinline__ uint4 ld_b128(const uint32_t* p) {
  uint4 r;
  asm volatile("{ .reg .b64 u, v; .reg .b128 w; ld.relaxed.gpu.global.b128 w, [%4]; mov.b128 {u, v}, w; mov.b64 {%0, %1}, u; mov.b64 {%2, %3}, v; }"
               : "=r"(r.x), "=r"(r.y), "=r"(r.z), "=r"(r.w) : "l"(p) : "memory");
  return r;
}
__device__ __forceinline__ void st_pairs(uint32_t* p, uint32_t a, uint32_t b, uint32_t tag) {
  asm volatile("{ .reg .b64 u, v; mov.b64 u, {%1, %3}; mov.b64 v, {%2, %3}; st.relaxed.gpu.global.v2.b64 [%0], {u, v}; }"
               ::"l"(p), "r"(a), "r"(b), "r"(tag) : "memory");
}
__device__ __forceinline__ uint4 ld_pairs(const uint32_t* p) {
  uint4 v;
  asm volatile("{ .reg .b64 u, v; ld.relaxed.gpu.global.v2.b64 {u, v}, [%4]; mov.b64 {%0, %1}, u; mov.b64 {%2, %3}, v; }"
               : "=r"(v.x), "=r"(v.y), "=r"(v.z), "=r"(v.w) : "l"(p) : "memory");
  return v;
}
__device__ __forceinline__ uint2 ld_pair(const uint32_t* p) {
  uint2 v;
  asm volatile("{ .reg .b64 u; ld.relaxed.gpu.global.b64 u, [%2]; mov.b64 {%0, %1}, u; }" : "=r"(v.x), "=r"(v.y) : "l"(p) : "memory");
  return v;
}
__device__ __forceinline__ void red_release(uint32_t* p, uint32_t v) {
  asm volatile("red.release.gpu.global.add.u32 [%0], %1;" ::"l"(p), "r"(v) : "memory");
}
__device__ __forceinline__ uint32_t ldg_nc1(const void* p) {
  uint32_t v;
  asm volatile("ld.global.nc.u32 %0, [%1];" : "=r"(v) : "l"(p));
  return v;
}
__device__ __forceinline__ uint4 ldg_nc4(const void* p) {
  uint4 v; asm volatile("ld.global.nc.L1::no_allocate.v4.u32 {%0,%1,%2,%3}, [%4];" : "=r"(v.x), "=r"(v.y), "=r"(v.z), "=r"(v.w) : "l"(p)); return v;
}
__device__ __forceinline__ uint4 ldg_stream4(const void* p) {
  uint4 v;
  asm volatile("ld.global.nc.L1::no_allocate.L2::cache_hint.v4.u32 {%0,%1,%2,%3}, [%4], %5;" : "=r"(v.x), "=r"(v.y), "=r"(v.z), "=r"(v.w) : "l"(p), "l"(l2_stream()));
  return v;
}
__device__ __forceinline__ void stg4(void* p, uint4 v) {
  asm volatile("st.global.v4.u32 [%0], {%1,%2,%3,%4};" ::"l"(p), "r"(v.x), "r"(v.y), "r"(v.z), "r"(v.w) : "memory");
}
__device__ __forceinline__ void wait_counter(const uint32_t* p, uint32_t target) {
  uint32_t n = 0;
  while (__any_sync(0xffffffffu, (int)(ld_acquire(p) - target) < 0)) { watchdog(n); }
}
__device__ __forceinline__ uint32_t tagf(float v, uint32_t tag) { return (__float_as_uint(v) & ~3u) | tag; }
__device__ __forceinline__ bool tag_ok(uint4 v, uint32_t tag) { return (((v.x ^ tag) | (v.y ^ tag) | (v.z ^ tag) | (v.w ^ tag)) & 3u) == 0; }
__device__ __forceinline__ float untag_sum(uint32_t a, uint32_t b) { return __uint_as_float(a & ~3u) + __uint_as_float(b & ~3u); }
__device__ __forceinline__ uint4 poll4(const uint32_t* p, uint32_t tag) {
  uint4 v = ld_relaxed4(p);
  uint32_t n = 0;
  while (!__all_sync(0xffffffffu, tag_ok(v, tag))) { v = ld_relaxed4(p); watchdog(n); }
  return v;
}
__device__ __forceinline__ float bf_lo(uint32_t v) { return __uint_as_float(v << 16); }
__device__ __forceinline__ float bf_hi(uint32_t v) { return __uint_as_float(v & 0xffff0000u); }
__device__ __forceinline__ uint32_t pack_bf(float lo, float hi) {
  uint32_t r; asm("cvt.rn.bf16x2.f32 %0, %1, %2;" : "=r"(r) : "f"(hi), "f"(lo)); return r;
}
__device__ __forceinline__ float rbf(float v) { return __uint_as_float(pack_bf(0.f, v) & 0xffff0000u); }
__device__ __forceinline__ uint32_t hmul2(uint32_t a, uint32_t b) {
  uint32_t r; asm("mul.rn.bf16x2 %0, %1, %2;" : "=r"(r) : "r"(a), "r"(b)); return r;
}
__device__ __forceinline__ uint32_t hadd2(uint32_t a, uint32_t b) {
  uint32_t r; asm("add.rn.bf16x2 %0, %1, %2;" : "=r"(r) : "r"(a), "r"(b)); return r;
}
__device__ __forceinline__ uint32_t hsub2(uint32_t a, uint32_t b) {
  uint32_t r; asm("sub.rn.bf16x2 %0, %1, %2;" : "=r"(r) : "r"(a), "r"(b)); return r;
}
__device__ __forceinline__ uint32_t hmax2(uint32_t a, uint32_t b) {
  uint32_t r; asm("max.bf16x2 %0, %1, %2;" : "=r"(r) : "r"(a), "r"(b)); return r;
}
__device__ __forceinline__ float rcp(float x) { float r; asm("rcp.approx.ftz.f32 %0, %1;" : "=f"(r) : "f"(x)); return r; }
__device__ __forceinline__ float ex2(float x) { float r; asm("ex2.approx.ftz.f32 %0, %1;" : "=f"(r) : "f"(x)); return r; }
__device__ __forceinline__ void stmatrix4(uint32_t addr, uint32_t a, uint32_t b, uint32_t c, uint32_t d) {
  asm volatile("stmatrix.sync.aligned.m8n8.x4.shared.b16 [%0], {%1,%2,%3,%4};" ::"r"(addr), "r"(a), "r"(b), "r"(c), "r"(d) : "memory");
}
__device__ __forceinline__ void ldmatrix4(uint32_t addr, uint32_t& a, uint32_t& b, uint32_t& c, uint32_t& d) {
  asm volatile("ldmatrix.sync.aligned.m8n8.x4.shared.b16 {%0,%1,%2,%3}, [%4];" : "=r"(a), "=r"(b), "=r"(c), "=r"(d) : "r"(addr) : "memory");
}
__device__ __forceinline__ void ldmatrix4t(uint32_t addr, uint32_t& a, uint32_t& b, uint32_t& c, uint32_t& d) {
  asm volatile("ldmatrix.sync.aligned.m8n8.x4.trans.shared.b16 {%0,%1,%2,%3}, [%4];" : "=r"(a), "=r"(b), "=r"(c), "=r"(d) : "r"(addr) : "memory");
}
__device__ __forceinline__ void mma16816(float (&d)[4], uint32_t a0, uint32_t a1, uint32_t a2, uint32_t a3, uint32_t b0, uint32_t b1) {
  asm volatile("mma.sync.aligned.m16n8k16.row.col.f32.bf16.bf16.f32 {%0,%1,%2,%3}, {%4,%5,%6,%7}, {%8,%9}, {%0,%1,%2,%3};"
               : "+f"(d[0]), "+f"(d[1]), "+f"(d[2]), "+f"(d[3]) : "r"(a0), "r"(a1), "r"(a2), "r"(a3), "r"(b0), "r"(b1));
}
__device__ __forceinline__ void sts1(uint32_t a, uint32_t v) { asm volatile("st.shared.u32 [%0], %1;" ::"r"(a), "r"(v) : "memory"); }
__device__ __forceinline__ uint4 lds4(uint32_t a) {
  uint4 v; asm volatile("ld.shared.v4.u32 {%0,%1,%2,%3}, [%4];" : "=r"(v.x), "=r"(v.y), "=r"(v.z), "=r"(v.w) : "r"(a) : "memory"); return v;
}
__device__ __forceinline__ uint2 lds2(uint32_t a) {
  uint2 v; asm volatile("ld.shared.v2.u32 {%0,%1}, [%2];" : "=r"(v.x), "=r"(v.y) : "r"(a) : "memory"); return v;
}
__device__ __forceinline__ uint32_t lds1(uint32_t a) {
  uint32_t v; asm volatile("ld.shared.u32 %0, [%1];" : "=r"(v) : "r"(a) : "memory"); return v;
}
__device__ __forceinline__ void sts2(uint32_t a, uint32_t x, uint32_t y) { asm volatile("st.shared.v2.u32 [%0], {%1,%2};" ::"r"(a), "r"(x), "r"(y) : "memory"); }
__device__ __forceinline__ void sts4(uint32_t a, uint4 v) {
  asm volatile("st.shared.v4.u32 [%0], {%1,%2,%3,%4};" ::"r"(a), "r"(v.x), "r"(v.y), "r"(v.z), "r"(v.w) : "memory");
}
__device__ __forceinline__ float silu_f(float v) { return __fdividef(v, 1.f + __expf(-v)); }
__device__ __forceinline__ uint32_t hfma2(uint32_t a, uint32_t b, uint32_t c) {
  uint32_t r; asm("fma.rn.bf16x2 %0, %1, %2, %3;" : "=r"(r) : "r"(a), "r"(b), "r"(c)); return r;
}
__device__ __forceinline__ void split_inv(float sd, uint32_t& ih, uint32_t& il) {
  const float inv = rcp(sd);
  ih = pack_bf(inv, inv);
  const float lo = inv - bf_lo(ih);
  il = pack_bf(lo, lo);
}
__device__ __forceinline__ uint32_t ln_norm(uint32_t x, uint32_t mean2, uint32_t ih, uint32_t il) {
  const uint32_t d = hsub2(x, mean2);
  return hfma2(d, ih, hmul2(d, il));
}
__device__ __forceinline__ uint32_t modul(uint32_t n, uint32_t c1, uint32_t sh) { return hadd2(hmul2(n, c1), sh); }
__device__ __forceinline__ uint32_t ln_mod(uint32_t x, uint32_t mean2, uint32_t ih, uint32_t il, uint32_t c1, uint32_t sh) {
  return modul(ln_norm(x, mean2, ih, il), c1, sh);
}

#define R8(a, i) "+f"(a[i]), "+f"(a[i + 1]), "+f"(a[i + 2]), "+f"(a[i + 3]), "+f"(a[i + 4]), "+f"(a[i + 5]), "+f"(a[i + 6]), "+f"(a[i + 7])
#define D64 "{%0,%1,%2,%3,%4,%5,%6,%7,%8,%9,%10,%11,%12,%13,%14,%15,%16,%17,%18,%19,%20,%21,%22,%23,%24,%25,%26,%27,%28,%29,%30,%31," \
            "%32,%33,%34,%35,%36,%37,%38,%39,%40,%41,%42,%43,%44,%45,%46,%47,%48,%49,%50,%51,%52,%53,%54,%55,%56,%57,%58,%59,%60,%61,%62,%63}"
template <int TB>
__device__ __forceinline__ void mma_ss(float (&d)[64], uint64_t da, uint64_t db, int sc) {
  asm volatile("{\n.reg .pred p;\nsetp.ne.b32 p, %66, 0;\n"
               "wgmma.mma_async.sync.aligned.m64n128k16.f32.bf16.bf16 " D64 ", %64, %65, p, 1, 1, 0, %67;\n}"
               : R8(d, 0), R8(d, 8), R8(d, 16), R8(d, 24), R8(d, 32), R8(d, 40), R8(d, 48), R8(d, 56)
               : "l"(da), "l"(db), "r"(sc), "n"(TB));
}
template <int TB>
__device__ __forceinline__ void mma_rs(float (&d)[64], uint32_t a0, uint32_t a1, uint32_t a2, uint32_t a3, uint64_t db, int sc) {
  asm volatile("{\n.reg .pred p;\nsetp.ne.b32 p, %69, 0;\n"
               "wgmma.mma_async.sync.aligned.m64n128k16.f32.bf16.bf16 " D64 ", {%64,%65,%66,%67}, %68, p, 1, 1, %70;\n}"
               : R8(d, 0), R8(d, 8), R8(d, 16), R8(d, 24), R8(d, 32), R8(d, 40), R8(d, 48), R8(d, 56)
               : "r"(a0), "r"(a1), "r"(a2), "r"(a3), "l"(db), "r"(sc), "n"(TB));
}
#define D128 "{%0,%1,%2,%3,%4,%5,%6,%7,%8,%9,%10,%11,%12,%13,%14,%15,%16,%17,%18,%19,%20,%21,%22,%23,%24,%25,%26,%27,%28,%29,%30,%31," \
             "%32,%33,%34,%35,%36,%37,%38,%39,%40,%41,%42,%43,%44,%45,%46,%47,%48,%49,%50,%51,%52,%53,%54,%55,%56,%57,%58,%59,%60,%61,%62,%63," \
             "%64,%65,%66,%67,%68,%69,%70,%71,%72,%73,%74,%75,%76,%77,%78,%79,%80,%81,%82,%83,%84,%85,%86,%87,%88,%89,%90,%91,%92,%93,%94,%95," \
             "%96,%97,%98,%99,%100,%101,%102,%103,%104,%105,%106,%107,%108,%109,%110,%111,%112,%113,%114,%115,%116,%117,%118,%119,%120,%121,%122,%123,%124,%125,%126,%127}"
#define R128(d, e) R8(d, 0), R8(d, 8), R8(d, 16), R8(d, 24), R8(d, 32), R8(d, 40), R8(d, 48), R8(d, 56), \
                   R8(e, 0), R8(e, 8), R8(e, 16), R8(e, 24), R8(e, 32), R8(e, 40), R8(e, 48), R8(e, 56)
__device__ __forceinline__ void mma256_ss(float (&d)[64], float (&e)[64], uint64_t da, uint64_t db, int sc) {
  asm volatile("{\n.reg .pred p;\nsetp.ne.b32 p, %130, 0;\n"
               "wgmma.mma_async.sync.aligned.m64n256k16.f32.bf16.bf16 " D128 ", %128, %129, p, 1, 1, 0, 1;\n}"
               : R128(d, e) : "l"(da), "l"(db), "r"(sc));
}
__device__ __forceinline__ void mma256_rs(float (&d)[64], float (&e)[64], uint32_t a0, uint32_t a1, uint32_t a2, uint32_t a3, uint64_t db) {
  asm volatile("{\n.reg .pred p;\nsetp.ne.b32 p, 1, 0;\n"
               "wgmma.mma_async.sync.aligned.m64n256k16.f32.bf16.bf16 " D128 ", {%128,%129,%130,%131}, %132, p, 1, 1, 1;\n}"
               : R128(d, e) : "r"(a0), "r"(a1), "r"(a2), "r"(a3), "l"(db));
}
template <int N> __device__ __forceinline__ void keep(float (&a)[N]) {
#pragma unroll
  for (int i = 0; i < N; i++) asm volatile("" : "+f"(a[i])::"memory");
}
template <int N> __device__ __forceinline__ void keep(uint32_t (&a)[N]) {
#pragma unroll
  for (int i = 0; i < N; i++) asm volatile("" : "+r"(a[i])::"memory");
}

#define STAMP(idx) do {} while (0)
#define PROF(grp, cond, idx) do {} while (0)

constexpr float SCL2 = 1.4426950408889634f * 0.08838834764831845f;

__device__ __forceinline__ void pack_p(const float (&s)[64], uint32_t (&p)[32]) {
#pragma unroll
  for (int i = 0; i < 32; i++) p[i] = pack_bf(s[2 * i], s[2 * i + 1]);
}

__device__ __forceinline__ void issue_qk(float (&s)[64], uint32_t q0, uint32_t q1, uint32_t kslot) {
  const uint64_t db = make_desc(kslot, 16, 1024), da0 = make_desc(q0, 16, 1024), da1 = make_desc(q1, 16, 1024);
#pragma unroll
  for (int kk = 0; kk < 8; kk++) mma_ss<0>(s, (kk < 4 ? da0 : da1) + (kk & 3) * 2, db + (kk >> 2) * 1024 + (kk & 3) * 2, kk != 0);
}
__device__ __forceinline__ void issue_pv(float (&o)[64], uint32_t (&p)[32], uint32_t vslot, int acc) {
  uint64_t db = make_desc(vslot, 16384, 1024);
#pragma unroll
  for (int kk = 0; kk < 8; kk++)
    mma_rs<1>(o, p[4 * kk], p[4 * kk + 1], p[4 * kk + 2], p[4 * kk + 3], db + kk * 128, kk == 0 ? acc : 1);
}

template <int H>
__device__ __forceinline__ void store_chunk(const float (&a)[64], uint32_t addr) {
#pragma unroll
  for (int i = 8 * H; i < 8 * H + 8; i += 2)
    stmatrix4(addr ^ ((i & 7) << 4), pack_bf(a[4 * i], a[4 * i + 1]), pack_bf(a[4 * i + 2], a[4 * i + 3]),
              pack_bf(a[4 * i + 4], a[4 * i + 5]), pack_bf(a[4 * i + 6], a[4 * i + 7]));
}
template <int H>
__device__ __forceinline__ void store_chunk(const float (&a)[64], float i0, float i1, uint32_t addr) {
#pragma unroll
  for (int i = 8 * H; i < 8 * H + 8; i += 2)
    stmatrix4(addr ^ ((i & 7) << 4), pack_bf(a[4 * i] * i0, a[4 * i + 1] * i0), pack_bf(a[4 * i + 2] * i1, a[4 * i + 3] * i1),
              pack_bf(a[4 * i + 4] * i0, a[4 * i + 5] * i0), pack_bf(a[4 * i + 6] * i1, a[4 * i + 7] * i1));
}
__device__ __forceinline__ float inv_quad_sum(float l) {
  l += __shfl_xor_sync(0xffffffffu, l, 1);
  l += __shfl_xor_sync(0xffffffffu, l, 2);
  return rcp(l);
}

__device__ __forceinline__ void ln_scalars(float mean, float var, float& mb, float& sd) {
  mb = rbf(mean);
  float r; asm("sqrt.approx.ftz.f32 %0, %1;" : "=f"(r) : "f"(rbf(rbf(var) + 1e-5f)));
  sd = rbf(r);
}

__global__ void __cluster_dims__(2, 1, 1) __launch_bounds__(384, 1) fused_kernel(const __grid_constant__ Maps maps, const Ptrs P) {
  extern __shared__ __align__(1024) uint8_t smem_raw[];
  const uint32_t base = smem_u32(smem_raw);
  const int tid = threadIdx.x, lane = tid & 31;
  const int warp = __shfl_sync(0xffffffffu, tid >> 5, 0);
  const int b = blockIdx.x;
  PROF(31, tid == 0, 0);

  if (b >= NMAIN) {
    float* sc = reinterpret_cast<float*>(smem_raw);
    float* red = sc + DM;
    for (int k = tid; k < DM; k += 384) sc[k] = rbf(silu_f(__bfloat162float(P.c[k])));
    __syncthreads();
    if (tid < 256) {
      const int col = 2048 + (b - NMAIN) * 1024 + (tid & 127) * 8, r0 = (tid >> 7) * 512;
      float acc[8];
#pragma unroll
      for (int e = 0; e < 8; e++) acc[e] = 0.f;
#pragma unroll 1
      for (int r = r0; r < r0 + 512; r += HU) {
        uint4 w[HU];
#pragma unroll
        for (int u = 0; u < HU; u++) w[u] = ldg_stream4(P.w_mod + (size_t)(r + u) * NMOD + col);
#pragma unroll
        for (int u = 0; u < HU; u++) {
          float s = sc[r + u];
          acc[0] += s * bf_lo(w[u].x); acc[1] += s * bf_hi(w[u].x); acc[2] += s * bf_lo(w[u].y); acc[3] += s * bf_hi(w[u].y);
          acc[4] += s * bf_lo(w[u].z); acc[5] += s * bf_hi(w[u].z); acc[6] += s * bf_lo(w[u].w); acc[7] += s * bf_hi(w[u].w);
        }
      }
      if (tid >= 128) {
#pragma unroll
        for (int e = 0; e < 8; e++) red[(tid & 127) * 8 + e] = acc[e];
      }
      const uint32_t tag = ld_relaxed(&g_epoch) % 3 + 1;
      bar_sync(1, 256);
      if (tid < 128) {
        uint32_t o[8];
#pragma unroll
        for (int e = 0; e < 8; e++) o[e] = __float_as_uint(rbf(acc[e] + red[tid * 8 + e])) | tag;
        st_relaxed4(g_mod + col, o[0], o[1], o[2], o[3]);
        st_relaxed4(g_mod + col + 4, o[4], o[5], o[6], o[7]);
        const uint4 wr = ldg_nc4(P.w_r + tid * 8);
        const uint32_t wv[4] = {wr.x, wr.y, wr.z, wr.w};
        float dsum = 0.f;
#pragma unroll
        for (int e = 0; e < 8; e++) {
          const float m = bf_hi(o[e]);
          dsum += (b == NMAIN + 2 ? rbf(1.f + m) : m) * ((e & 1) ? bf_hi(wv[e >> 1]) : bf_lo(wv[e >> 1]));
        }
#pragma unroll
        for (int k = 16; k > 0; k >>= 1) dsum += __shfl_xor_sync(0xffffffffu, dsum, k);
        if (lane == 0) st_relaxed(g_mod + (b - NMAIN) * 4 + warp, tagf(dsum, tag));
      }
    }
    PROF(2, tid == 0, 1);
    return;
  }

  const int rank = b & 1;
  const int rb = ((b >> 4) << 1) | rank, cj = (b >> 1) & 7;
  const uint32_t bfull = base + OFF_BAR, bempty = bfull + NSLOT * 8;
  const uint32_t gfull = bempty + NSLOT * 8, gempty = gfull + 32;
  const uint32_t bar_ofull = gempty + 32;
  const uint32_t bar_ofree = bar_ofull + 32;
  const uint32_t bar_par = bar_ofree + 32;
  const uint32_t bar_mod = bar_par + 8;
  const uint32_t bar_pread = bar_mod + 8;
  const uint32_t bar_xres = bar_pread + 8;
  const uint32_t bar_ring = bar_xres + 8;
  const uint32_t bar_box = bar_ring + 24;
  const uint32_t bar_go = bar_box + 96;
  const uint32_t bar_go2 = bar_go + 16;
  const uint32_t bar_cnt = bar_go + 24;
  const uint32_t xfull = bar_go + 40, xempty = xfull + 32;
  const uint32_t bar_hw = xempty + 32, bar_hx = bar_hw + 8;
  const uint32_t bar_hpub = bar_hx + 16;
  const uint32_t bar_win = bar_hpub + 16;
  const uint32_t bar_rx = bar_win + 8;
  const uint32_t bar_sel = bar_rx + 8;
  const uint32_t bar_gate = bar_sel + 8;
  const uint32_t bar_rel = bar_gate + 8;
  const uint32_t bar_od = bar_rel + 8;
  const uint32_t bar_res = bar_go + 8;
  const uint32_t stage = base + OFF_STAGE, par = base + OFF_PAR;

  if (warp == 8 && elect_one()) {
    for (int s = 0; s < NSLOT; s++) { mbar_init(bfull + s * 8, 1); mbar_init(bempty + s * 8, 16); }
    for (int s = 0; s < 4; s++) { mbar_init(gfull + s * 8, 1); mbar_init(gempty + s * 8, 16); mbar_init(xfull + s * 8, 1); mbar_init(xempty + s * 8, 8); mbar_init(bar_ofree + s * 8, 1); mbar_init(bar_ofull + s * 8, 128); }
    mbar_init(bar_par, 64); mbar_init(bar_mod, 256); mbar_init(bar_pread, 2); mbar_init(bar_xres, 1);
    mbar_init(bar_ring, 8); mbar_init(bar_ring + 8, 8); mbar_init(bar_ring + 16, 8);
    mbar_init(bar_go, 1); mbar_init(bar_go2, 1); mbar_init(bar_cnt, 1); mbar_init(bar_cnt + 8, 1); mbar_init(bar_hpub, 8); mbar_init(bar_hpub + 8, 8); mbar_init(bar_res, 1); mbar_init(bar_win, 1); mbar_init(bar_rx, 1); mbar_init(bar_sel, 64); mbar_init(bar_gate, 8); mbar_init(bar_rel, 8); mbar_init(bar_od, 1);
    for (int s = 0; s < 12; s++) mbar_init(bar_box + s * 8, 1);
    asm volatile("fence.mbarrier_init.release.cluster;" ::: "memory");
    prefetch_map(&maps.x); prefetch_map(&maps.wq); prefetch_map(&maps.k); prefetch_map(&maps.v);
  }
  if (warp == 9 && elect_one()) {
    mbar_init(bar_hw, 1); mbar_init(bar_hx, 1); mbar_init(bar_hx + 8, 1);
    asm volatile("fence.mbarrier_init.release.cluster;" ::: "memory");
    mbar_expect_tx(bar_hw, 32768);
    mbar_expect_tx(bar_hx, 16384);
    mbar_expect_tx(bar_hx + 8, 16384);
    const __nv_bfloat16* xs = P.x + (size_t)(rb * 128 + cj * 16) * DM;
    bulk_load(base + 2 * GST_BYTES, xs, 16384, bar_hx);
    tma2d(stage, &maps.wm, (b >> 1) * 32, rank * 512, bar_hw);
    tma2d(stage + 16384, &maps.wm, (b >> 1) * 32, rank * 512 + 256, bar_hw);
    bulk_load(base + 3 * GST_BYTES, xs + 8 * DM, 16384, bar_hx + 8);
  }
  cluster_arrive();

  if (warp >= 8) {
    asm volatile("setmaxnreg.dec.sync.aligned.u32 40;");
    if (warp < 10) bar_arrive(1, 320);
    const uint32_t epoch = ld_relaxed(&g_epoch);
    cluster_wait();
    if (warp == 8) {
      const int kvrow = (cj >> 1) * SK + (SK - WIN);
      int wch = cj * 8 + rank * 2;
#pragma unroll 1
      for (int ps = 0; ps < 3; ps++) {
        const CUtensorMap* mw = ps == 2 ? &maps.wo : &maps.wq;
        const uint32_t xt = ps == 1 ? XT1 : XT2, wt = ps == 0 ? WT0 : (ps == 1 ? WT1 : WT2);
        const int nst = ps == 2 ? 32 : 16;
#pragma unroll 1
        for (int i = 0; i < nst; i++) {
          const uint32_t bf = gfull + (i & 3) * 8;
          const int kt = ps == 2 ? (((cj & 1) * 4 + ((i >> 1) & 3)) * 4 + (i >> 3)) * 2 + (i & 1) : (i + (ps ? 0 : b & 14)) & 15;
          const uint32_t wd = base + unit_of(wt, i & 3) + rank * UNIT, xd = base + unit_of(xt, i & 3);
          const uint8_t* xs = g_act + (uint32_t)(rb * 80 + (ps - 1) * 16 + kt) * UNIT;
          if (ps == 0 && i == HD) mbar_wait(bar_mod, 0);
          const bool xfirst = ps && i < 2;
          if (ps == 2 && i == 0) mbar_wait(bar_ofree + 24, 0);
          if (i == 0) fence_async();
          mbar_wait(gempty + (i & 3) * 8, ((i >> 2) & 1) ^ 1);
          if (elect_one()) {
            mbar_expect_tx(bf, ps ? GST_BYTES : 2 * UNIT);
            if (xfirst) bulk_load_stream(xd, xs, UNIT, bf);
          }
          if (ps && i < 4) mbar_wait(bempty + i * 8, 1);
          if (elect_one()) tma3d_mc<true>(wd, mw, 0, (i == 31 ? kt ^ (rank * 32) : kt) * 64, i == 31 ? cj * 2 : wch, bf);
          if (ps) {
            if (i == 16 || i == 24) { mbar_wait(bar_cnt + i - 16, 0); fence_async(); }
            if (i == RES0) mbar_wait(bar_res, 0);
            if (i == 2) mbar_wait(bar_ofree + (ps - 1) * 16, 0);
            if (elect_one()) {
              if (i == 31) bulk_load(xd, xs, UNIT, bf); else if (!xfirst) bulk_load_stream(xd, xs, UNIT, bf);
              mbar_arrive_pred(bar_go, i == GOST - 1);
              if (PG0 < 16) mbar_arrive_pred(bar_go2, ps == 1 && i == PG0);
              mbar_arrive_pred(bar_od, i == (ps == 1 ? ODS1 : ODS));
              if (i == RES0) mbar_expect_tx(bar_xres, 32768);
              if (i == RES0 || i == RES1) tma2d(base + OFF_RES + (i == RES1) * UNIT, &maps.x, cj * 128 + (i == RES1) * 64, rb * 128, bar_xres);
            }
          }
        }
        if (ps == 2) break;
        wch = ps ? ((wch >> 3) ^ rank) * 2 : wch + 4;
#pragma unroll 1
        for (int u = 0; u < 16; u++) {
          const bool isk = (u == 0) || ((u & 1) && u < 15);
          const int blk = (isk ? (u + 1) >> 1 : (u == 15 ? 7 : (u >> 1) - 1)) & 3;
          const uint32_t sl = base + unit_of(ps ? AT1 : AT0, u & 3) + rank * UNIT, bf = bfull + (u & 3) * 8;
          if (u < 4) mbar_wait(gempty + ((u + 1) >> 1) * 8, 1);
          mbar_wait(bempty + (u & 3) * 8, ((u >> 2) & 1) ^ 1);
          if (elect_one()) {
            mbar_arrive_pred(bar_go2, ps && u + 16 == PG0);
            mbar_expect_tx(bf, SLOT_BYTES);
            tma3d_mc<false>(sl, isk ? &maps.k : &maps.v, 0, kvrow + blk * 128, rank, bf);
          }
        }
      }
      if (elect_one()) mbar_expect_tx(bar_rx, UNIT);
      mbar_wait(bar_rel, 0);
      if (elect_one()) {
        bulk_load_stream(base + UNIT, g_act + (uint32_t)(rb * 80 + 16 + 63 - (cj & 1) * 32) * UNIT, UNIT, bar_rx);
      }
      if (b < NFFN) {
#pragma unroll 1
        for (int u = 0; u < 12; u++) {
          const uint32_t dst = base + unit_of(u < 4 ? FT_G : (u < 8 ? FT_U : FT_D), u & 3);
          if (elect_one()) mbar_expect_tx(bar_box + u * 8, UNIT);
          if (u == FB0 || u == 2 || u == FB2) mbar_wait(bar_ring + (u == FB2 ? 16 : (u + 6) & 8), 0);
          if (u >= FPACE) mbar_wait(bar_box + (u - FPACE) * 8, 0);
          if (elect_one()) {
            if (u < 8) tma2d(dst, u < 4 ? &maps.wg : &maps.wu, b * 32, (u & 3) * 256, bar_box + u * 8);
            else tma3d(dst, &maps.wd, 0, b * 32, (u - 8) * 4, bar_box + u * 8);
          }
        }
      }
    } else if (warp == 9) {
      const uint32_t target = 8 * (epoch + 1);
      uint32_t hmask = 0;
#pragma unroll 1
      for (int i = 0; i < 16; i++) {
        if (i == HDX) mbar_wait(bar_mod, 0);
        const uint32_t need = i == 15 ? 0xffffu : 1u << ((2 * cj + i) & 15);
        if (i >= NRS && (hmask & need) != need) {
          uint32_t n = 0;
          do { hmask = __ballot_sync(0xffffffffu, ld_acquire(&g_cnt_h[rb * 32 + (lane & 15)]) == epoch + 1); watchdog(n); } while ((hmask & need) != need);
          PROF(1, lane == 0 && i == NRS, 26);
          fence_async();
        }
        mbar_wait(xempty + (i & 3) * 8, ((i >> 2) & 1) ^ 1);
        if (elect_one()) {
          mbar_expect_tx(xfull + (i & 3) * 8, UNIT);
          if (i < NRS) tma2d(base + (i & 3) * GST_BYTES, &maps.x, ((2 * cj + i) & 15) * 64, rb * 128, xfull + (i & 3) * 8);
          else bulk_load_stream(base + (i & 3) * GST_BYTES, g_act + (uint32_t)(rb * 80 + ((2 * cj + i) & 15)) * UNIT, UNIT, xfull + (i & 3) * 8);
        }
      }
      prefetch_map(&maps.wo);
#pragma unroll 1
      for (int t = 0; t < 4; t++) {
        if (t & 1) mbar_wait(bar_od, t >> 1);
#pragma unroll 1
        for (int p = 0; p < 32768 / OPS; p++) {
          const uint32_t w = p / (16384 / OPS), c = (p / (8192 / OPS)) & 1, off = w * 8192 + (p % (8192 / OPS)) * OPS;
          mbar_wait(bar_ofull + (t & 1) * 16 + w * 8, t >> 1);
          if (elect_one()) {
            bulk_store(g_act + (uint32_t)(rb * 80 + 16 + (cj * 4 + t) * 2 + c) * UNIT + off, base + unit_of(QT, 2 * t + c) + off, OPS);
            asm volatile("cp.async.bulk.commit_group;" ::: "memory");
            asm volatile("cp.async.bulk.wait_group.read %0;" ::"n"(OFL) : "memory");
          }
        }
        if (elect_one()) {
          asm volatile("cp.async.bulk.wait_group.read 0;" ::: "memory");
          mbar_arrive(t < 3 ? bar_ofree + t * 8 : bar_res);
          asm volatile("cp.async.bulk.wait_group 0;" ::: "memory");
          fence_async();
          red_release(&g_cnt_o[((rb * 4 + t) * 2 + (cj >> 2)) * 32], 2);
        }
        if (t) {
          wait_counter(&g_cnt_o[(rb * 8 + 2 * t + (cj & 1)) * 32], target);
          if (t & 1) wait_counter(&g_cnt_o[(rb * 8 + (t == 1 ? cj & 1 : 7 - (cj & 1))) * 32], target);
          if (elect_one()) mbar_arrive(t == 1 ? bar_ofree + 24 : bar_cnt + t * 8 - 16);
        }
      }
      PROF(2, lane == 0, 27);
      const uint32_t tag = epoch % 3 + 1;
      const uint32_t* inbox = g_cand + (lane & 15);
      mbar_wait(bar_ring + 16, 0);
      uint32_t c0 = ld_relaxed(inbox), n = 0;
#define CAND_STEP(cv)                                                                                        \
      {                                                                                                      \
        const bool valid = (cv & 3u) == tag, all = __all_sync(0xffffffffu, valid);                           \
        const uint32_t best = __reduce_max_sync(0xffffffffu, valid ? cv : 0u);                               \
        const uint32_t blk = __ffs(__ballot_sync(0xffffffffu, cv == best)) - 1;                              \
        if (best) sts2(par + PAR_CONST + 56, best, (blk << 7 | (~best >> 2 & 127)) | (all ? 0x1800 : 0x800)); \
        if (all) break;                                                                                      \
        cv = ld_relaxed(inbox);                                                                              \
      }
      while (true) { CAND_STEP(c0) watchdog(n); }
    } else {
      const int t2 = tid - 320;
      mbar_wait(bar_hpub + (warp & 1) * 8, 0);
      PROF(1, t2 == 0, 24);
      if (elect_one()) {
#pragma unroll 1
        for (int c = 0; c < UNIT / HPS; c++) {
          const uint32_t off = (warp & 1) * UNIT + c * HPS;
          bulk_store(g_act + (uint32_t)(rb * 80 + cj * 2) * UNIT + off, stage + off, HPS);
          asm volatile("cp.async.bulk.commit_group;" ::: "memory");
          asm volatile("cp.async.bulk.wait_group.read 0;" ::: "memory");
        }
        PROF(1, warp == 10, 15);
        mbar_arrive(bar_pread);
        asm volatile("cp.async.bulk.wait_group 0;" ::: "memory");
        fence_async();
        red_release(&g_cnt_h[rb * 32 + cj * 2 + (warp & 1)], 1);
        PROF(1, warp == 10, 25);
        prefetch_map(&maps.wg); prefetch_map(&maps.wu); prefetch_map(&maps.wd); prefetch_map(&maps.out);
      }
      __syncwarp();
      if (b < NFFN) {
        mbar_wait(bar_go2, 0);
        const __nv_bfloat16* pg = ((b & 1) ? P.w_up : P.w_gate) + (b >> 1) * 64 + (size_t)t2 * FF;
        const __nv_bfloat16* pd = P.w_down + (size_t)b * 32768 + t2 * 64;
        PROF(2, t2 == 0, 13);
#pragma unroll 1
        for (int i = 0; i < WN; i += WB) {
          uint32_t v[WB];
#pragma unroll
          for (int u = 0; u < WB; u++) {
            const int k = i + u;
            asm volatile("ld.global.cg.L2::128B.u32 %0, [%1];" : "=r"(v[u]) : "l"(k < 16 ? pg + (size_t)k * 64 * FF : pd + (k - 16) * 4096));
          }
#pragma unroll
          for (int u = 1; u < WB; u++) v[0] ^= v[u];
          sts1(par + PAR_SINK + t2 * 4, v[0]);
        }
        PROF(2, t2 == 0, 14);
      }
      const uint32_t tag = epoch % 3 + 1;
      mbar_wait(bar_go, 0);
      if (warp == 10) {
        const uint32_t* src = g_mod + 2 * DM + cj * 128 + lane * 4;
        const uint2 wr = *reinterpret_cast<const uint2*>(P.w_r + cj * 128 + lane * 4);
        uint4 vga, vsb, vcb, vgb;
        uint32_t n = 0;
        do {
          vga = ld_relaxed4(src); vsb = ld_relaxed4(src + DM); vcb = ld_relaxed4(src + 2 * DM); vgb = ld_relaxed4(src + 3 * DM);
          watchdog(n);
        } while (!__all_sync(0xffffffffu, tag_ok(vga, tag) && tag_ok(vsb, tag) && tag_ok(vcb, tag) && tag_ok(vgb, tag)));
        const float c0 = rbf(1.f + bf_hi(vcb.x)), c1 = rbf(1.f + bf_hi(vcb.y)), c2 = rbf(1.f + bf_hi(vcb.z)), c3 = rbf(1.f + bf_hi(vcb.w));
        const float a0 = c0 * bf_lo(wr.x), a1 = c1 * bf_hi(wr.x), a2 = c2 * bf_lo(wr.y), a3 = c3 * bf_hi(wr.y);
        const uint32_t h0 = pack_bf(a0, a1), h1 = pack_bf(a2, a3);
        const uint32_t t1 = par + PAR_T1 + (lane >> 2) * 64 + (lane & 1) * 32 + (lane & 2) * 2;
        sts1(t1, h0); sts1(t1 + 8, pack_bf(a0 - bf_lo(h0), a1 - bf_hi(h0)));
        sts1(t1 + 16, h1); sts1(t1 + 24, pack_bf(a2 - bf_lo(h1), a3 - bf_hi(h1)));
        sts4(par + PAR_T2 + lane * 32, make_uint4(pack_bf(c0, c1), __byte_perm(vsb.x, vsb.y, 0x7632), __byte_perm(vgb.x, vgb.y, 0x7632), __byte_perm(vga.x, vga.y, 0x7632)));
        sts4(par + PAR_T2 + lane * 32 + 16, make_uint4(pack_bf(c2, c3), __byte_perm(vsb.z, vsb.w, 0x7632), __byte_perm(vgb.z, vgb.w, 0x7632), __byte_perm(vga.z, vga.w, 0x7632)));
      } else {
        const uint4 g = poll4((lane & 2) ? g_mod + 8 - (lane & 1) * 4 : g_mod + 5 * DM + b * 8 + (lane & 1) * 4, tag);
        sts1(par + PAR_CONST + 60, 0);
        if (lane < 2) sts4(par + PAR_CONST + 16 + lane * 16, g);
        else if (lane < 4) sts2(par + PAR_CONST + (lane - 2) * 8, __float_as_uint(untag_sum(g.x, g.y) + untag_sum(g.z, g.w)), epoch);
      }
      __syncwarp();
#pragma unroll 4
      for (int q = 0; q < 32; q++) st_b128(g_xch + ((size_t)b * 8 * 256 + q * 64 + t2) * 4, (epoch & 1) << 16, 0, 0, 0);
      for (int q = 0; q < 2; q++) st_relaxed4(g_stats + ((size_t)cj * SEQ + rb * 128 + q * 64 + t2) * 4, 0, 0, 0, 0);
      if (b < NFFN)
        for (int q = 0; q < 4; q++) st_relaxed4(g_ypart + ((size_t)(q * 32 + (t2 >> 1)) * NFFN + b) * 8 + (t2 & 1) * 4, 0, 0, 0, 0);
      st_relaxed4(g_row + rb * 2 * DM + (t2 >> 5) * DM + cj * 128 + (t2 & 31) * 4, 0, 0, 0, 0);
      __threadfence();
      mbar_arrive(bar_par);
      mbar_wait(bar_gate, 0);
      uint32_t have = 0, n = 0;
      while (true) {
        const uint32_t st = lds1(par + PAR_CONST + 60) >> 7;
        if ((st & 31) != have) {
          const uint32_t* hsrc = g_row + (st & 15) * 2 * DM + t2 * 4;
          uint4 hv[4];
          bool ok = true;
#pragma unroll
          for (int i = 0; i < 4; i++) hv[i] = ld_pairs(hsrc + i * 256);
#pragma unroll
          for (int i = 0; i < 4; i++) {
            sts2(base + ((FT_G >> i * 4) & 15) * UNIT + (warp & 1) * 8192 + 256 + lane * 8, hv[i].x, hv[i].z);
            ok = ok && hv[i].y == tag && hv[i].w == tag;
          }
          have = __all_sync(0xffffffffu, ok) ? st & 31 : 0;
        }
        if ((st ^ have) == 32) break;
        watchdog(n);
      }
      mbar_arrive(bar_sel);
    }
    __syncwarp();
    cluster_arrive();
    {
      const uint32_t tag = epoch % 3 + 1, t3 = tid - 256;
      mbar_wait(bar_win, 0);
      uint2 win = lds2(par + PAR_CONST + 56);
      win.y &= 0x7ff;
      const uint32_t* fsrc = g_row + (win.y >> 7) * 2 * DM + (b >> 1) * 16 + (t3 & 3) * 4 + (b & 1) * 2;
      const uint32_t* ysrc = g_ypart + (size_t)b * NFFN * 8 + min(t3, NFFN - 1) * 4;
      uint2 fh = ld_pair(fsrc), fx = ld_pair(fsrc + DM);
      if (PSL) __nanosleep(PSL);
      uint4 ya = ld_relaxed4(ysrc), yb = ld_relaxed4(ysrc + NFFN * 4);
      const float rwin = __uint_as_float(((int)win.x < 0 ? win.x & 0x7fffffffu : ~win.x) & ~0x1ffu);
      const float rs = rbf(rcp(1.f + __expf(-rbf(rwin))));
      uint32_t n = 0;
      while (__any_sync(0xffffffffu, fh.y != tag || fx.y != tag)) { fh = ld_pair(fsrc); fx = ld_pair(fsrc + DM); watchdog(n); }
      while (!__all_sync(0xffffffffu, tag_ok(ya, tag) && tag_ok(yb, tag))) {
        if (!tag_ok(ya, tag)) ya = ld_relaxed4(ysrc);
        if (!tag_ok(yb, tag)) yb = ld_relaxed4(ysrc + NFFN * 4);
        watchdog(n);
      }
      __syncwarp();
      PROF(8, t3 == 0, 5);
      float y0 = untag_sum(ya.x, yb.x), y1 = untag_sum(ya.y, yb.y), y2 = untag_sum(ya.z, yb.z), y3 = untag_sum(ya.w, yb.w);
      const bool u1 = lane & 2, u2 = lane & 4;
      y0 = (u1 ? y2 : y0) + __shfl_xor_sync(0xffffffffu, u1 ? y0 : y2, 2);
      y1 = (u1 ? y3 : y1) + __shfl_xor_sync(0xffffffffu, u1 ? y1 : y3, 2);
      y0 = (u2 ? y1 : y0) + __shfl_xor_sync(0xffffffffu, u2 ? y0 : y1, 4);
      y0 += __shfl_xor_sync(0xffffffffu, y0, 8);
      if (!(lane & 8)) sts1(par + PAR_RED + 64 + (t3 >> 4) * 32 + ((lane & 1) * 4 + (lane & 2) + ((lane >> 2) & 1)) * 4, __float_as_uint(y0));
      bar_sync(4, 128);
      if (t3 < 4) {
        y0 = 0.f; y1 = 0.f;
#pragma unroll
        for (int w4 = 0; w4 < 7; w4++) {
          const uint2 v = lds2(par + PAR_RED + 64 + w4 * 32 + t3 * 8);
          y0 += __uint_as_float(v.x); y1 += __uint_as_float(v.y);
        }
        const uint2 gv = lds2(par + PAR_CONST + 16 + t3 * 8);
        const uint32_t upd = hmul2(pack_bf(y0, y1), pack_bf(rs, rs));
        *reinterpret_cast<uint32_t*>(P.out + (size_t)win.y * DM + b * 8 + t3 * 2) =
            hadd2(fx.x, hmul2(__byte_perm(gv.x, gv.y, 0x7632), hadd2(fh.x, upd)));
        if (b == 0 && t3 == 0) st_relaxed(&g_epoch, epoch + 1);
      }
      PROF(31, t3 == 0, 36);
    }
    cluster_wait();
  } else {
    const int wg = warp >> 2;

    uint32_t tag;
    {
      uint32_t* const pmod = g_modp + rank * 2 * DM + (b >> 1) * 32 + lane;
      uint32_t* const pln = g_ln1 + (rb * 128 + cj * 16 + warp) * 4;
      const uint32_t cv = ldg_nc1(P.c + rank * 512 + tid * 2);
      const uint32_t epoch = ld_relaxed(&g_epoch);
      if (warp == 0) st_relaxed(pmod, 0);
      if (lane == 0) { st_b128(pln, 0, 0, 0, 0); st_b128(pln + 32, 0, 0, 0, 0); }
      asm volatile("setmaxnreg.inc.sync.aligned.u32 232;");
      sts1(par + tid * 4, pack_bf(silu_f(bf_lo(cv)), silu_f(bf_hi(cv))));
      bar_sync(1, 320);
      tag = epoch % 3 + 1;
#pragma unroll
      for (int part = 0; part < 3; part++) {
        if (part != 1) {
          const uint32_t xa = base + (2 + part / 2) * GST_BYTES + warp * 2048 + lane * 16;
          mbar_wait(bar_hx + part * 4, 0);
          float s0 = 0.f, s1 = 0.f, q0 = 0.f, q1 = 0.f;
#pragma unroll
          for (int q = 0; q < 4; q++) {
            const uint4 xv = lds4(xa + q * 512);
            const uint32_t u[4] = {xv.x, xv.y, xv.z, xv.w};
#pragma unroll
            for (int e = 0; e < 4; e++) { const float lo = bf_lo(u[e]), hi = bf_hi(u[e]); s0 += lo; s1 += hi; q0 += lo * lo; q1 += hi * hi; }
          }
          s0 += s1; q0 += q1;
#pragma unroll
          for (int o = 16; o > 0; o >>= 1) { s0 += __shfl_xor_sync(0xffffffffu, s0, o); q0 += __shfl_xor_sync(0xffffffffu, q0, o); }
          const float mean = s0 * (1.f / DM);
          float mb, sd;
          ln_scalars(mean, fmaxf(q0 * (1.f / DM) - mean * mean, 0.f), mb, sd);
          uint32_t ih, il;
          split_inv(sd, ih, il);
          if (lane == 0) st_b128(pln + part * 16, pack_bf(mb, mb), ih, il, tag);
          PROF(1, tid == 0 && part == 2, 4);
        } else {
          const uint32_t fr = (lane & 7) + (lane >> 4) * 8, tq = lane & 3;
          const uint32_t wa = stage + warp * 4096 + fr * 64 + ((((lane >> 3) & 1) ^ ((fr >> 1) & 3)) << 4);
          uint32_t sc[8];
#pragma unroll
          for (int k = 0; k < 8; k++) sc[k] = lds1(par + warp * 128 + k * 16 + tq * 4);
          float d0[4] = {0.f, 0.f, 0.f, 0.f}, d1[4] = {0.f, 0.f, 0.f, 0.f};
          mbar_wait(bar_hw, 0);
#pragma unroll
          for (int ks = 0; ks < 4; ks++) {
            uint32_t w[8];
            ldmatrix4t(wa + ks * 1024, w[0], w[1], w[2], w[3]);
            ldmatrix4t((wa ^ 32) + ks * 1024, w[4], w[5], w[6], w[7]);
            mma16816(d0, w[0], w[1], w[2], w[3], sc[2 * ks], sc[2 * ks + 1]);
            mma16816(d1, w[4], w[5], w[6], w[7], sc[2 * ks], sc[2 * ks + 1]);
          }
          sts1(base + 2 * GST_BYTES + warp * 2048 + (tq * 8 + (lane >> 2)) * 4, __float_as_uint((tq & 2) ? ((tq & 1) ? d1[2] : d1[0]) : ((tq & 1) ? d0[2] : d0[0])));
          bar_sync(1, 256);
          if (warp == 0) {
            float s = 0.f;
#pragma unroll
            for (int w8 = 0; w8 < 8; w8++) s += __uint_as_float(lds1(base + 2 * GST_BYTES + w8 * 2048 + lane * 4));
            st_relaxed(pmod, (__float_as_uint(s) & ~3u) | tag);
          }
          PROF(1, tid == 0, 3);
        }
      }
      cluster_wait();
      if (wg == 1) bar_arrive(2, 256);
    }

    float f0 = 0.f, f1 = 0.f;
    const uint32_t rempty = lane < 2 ? mapa(bempty, lane & 1) : 0;
    constexpr uint32_t GE = NSLOT * 8 + 32;
    float o[64], s[64];
#pragma unroll 1
    for (int ps = 0; ps < 3; ps++) {
      {
        const uint32_t xt = ps == 1 ? XT1 : XT2, wt = ps == 1 ? WT1 : WT2;
        const int nst = ps == 2 ? 28 : 14;
        if (ps == 0) {
          float ga[64], gb[64];
#pragma unroll
          for (int i = 0; i < 64; i++) { ga[i] = 0.f; gb[i] = 0.f; }
          uint32_t a[2][16];
          const uint32_t l = fresh_lane();
          uint32_t fa[4];
#pragma unroll
          for (int kk = 0; kk < 4; kk++) fa[kk] = (base + wg * 8192 + frag_offset(warp)) ^ (kk * 32);
          const uint32_t mt = par + (l & 3) * 16;
          auto fetch = [&](int i, uint32_t (&f)[16], uint32_t z) {
            mbar_wait(xfull + (i & 3) * 8, i >> 2);
#pragma unroll
            for (int kk = 0; kk < 4; kk++) ldmatrix4(fa[kk] + (i & 3) * GST_BYTES + z, f[4 * kk], f[4 * kk + 1], f[4 * kk + 2], f[4 * kk + 3]);
          };
          uint4 r0, r1;
          {
            const uint32_t t7 = (warp & 3) * 32 + l;
            const uint32_t* pm = g_modp + wg * DM + ((cj * 128 + t7 * 4) & (DM - 1));
            const uint32_t* pr = g_ln1 + (rb * 128 + warp * 16 + (l >> 2)) * 4;
            uint4 m0 = ld_relaxed4(pm), m1 = ld_relaxed4(pm + 2 * DM);
            r0 = ld_b128(pr); r1 = ld_b128(pr + 32);
            fetch(0, a[0], 0); fetch(1, a[1], 0);
            uint32_t n = 0;
            bool written = false;
#pragma unroll 1
            while (true) {
              uint32_t miss;
              asm volatile("{ .reg .pred p0, p1, p2, p3; .reg .b32 t, u;\n"
                           "lop3.b32 t, %1, %2, %19, 0x7e; lop3.b32 u, %3, %4, %19, 0x7e; or.b32 t, t, u; and.b32 t, t, 3; setp.ne.u32 p0, t, 0;\n"
                           "lop3.b32 t, %5, %6, %19, 0x7e; lop3.b32 u, %7, %8, %19, 0x7e; or.b32 t, t, u; and.b32 t, t, 3; setp.ne.u32 p1, t, 0;\n"
                           "setp.ne.u32 p2, %12, %19; setp.ne.u32 p3, %16, %19;\n"
                           "@p0 ld.relaxed.gpu.global.v4.u32 {%1, %2, %3, %4}, [%17];\n"
                           "@p1 ld.relaxed.gpu.global.v4.u32 {%5, %6, %7, %8}, [%17 + 8192];\n"
                           "@p2 ld.relaxed.gpu.global.v4.u32 {%9, %10, %11, %12}, [%18];\n"
                           "@p3 ld.relaxed.gpu.global.v4.u32 {%13, %14, %15, %16}, [%18 + 128];\n"
                           "or.pred p0, p0, p1; or.pred p2, p2, p3; vote.sync.any.pred p0, p0, 0xffffffff; vote.sync.any.pred p2, p2, 0xffffffff;\n"
                           "selp.u32 t, 1, 0, p0; selp.u32 u, 2, 0, p2; or.b32 %0, t, u; }"
                           : "=r"(miss), "+r"(m0.x), "+r"(m0.y), "+r"(m0.z), "+r"(m0.w), "+r"(m1.x), "+r"(m1.y), "+r"(m1.z), "+r"(m1.w),
                             "+r"(r0.x), "+r"(r0.y), "+r"(r0.z), "+r"(r0.w), "+r"(r1.x), "+r"(r1.y), "+r"(r1.z), "+r"(r1.w)
                           : "l"(pm), "l"(pr), "r"(tag) : "memory");
              if (!(miss & 1) && !written) {
                written = true;
                float c0 = untag_sum(m0.x, m1.x), c1 = untag_sum(m0.y, m1.y), c2 = untag_sum(m0.z, m1.z), c3 = untag_sum(m0.w, m1.w);
                if (wg) { c0 = 1.f + rbf(c0); c1 = 1.f + rbf(c1); c2 = 1.f + rbf(c2); c3 = 1.f + rbf(c3); }
                const uint32_t d = par + (t7 >> 2) * 64 + (t7 & 1) * 32 + (t7 & 2) * 2 + (wg ? 0 : 8);
                sts1(d, pack_bf(c0, c1));
                sts1(d + 16, pack_bf(c2, c3));
                mbar_arrive(bar_mod);
              }
              if (!miss) break;
              watchdog(n);
            }
          }
          const uint32_t zero = r0.w ^ tag;
          auto normalize = [&](uint32_t (&f)[16]) {
#pragma unroll
            for (int k = 0; k < 16; k += 2) { f[k] = ln_norm(f[k], r0.x, r0.y, r0.z); f[k + 1] = ln_norm(f[k + 1], r1.x, r1.y, r1.z); }
          };
          auto modulate = [&](int i, uint32_t (&f)[16]) {
#pragma unroll
            for (int kk = 0; kk < 4; kk++) {
              const uint4 m = lds4(mt + i * 256 + kk * 64);
              f[4 * kk] = MODUL(f[4 * kk], m.x, m.z); f[4 * kk + 1] = MODUL(f[4 * kk + 1], m.x, m.z);
              f[4 * kk + 2] = MODUL(f[4 * kk + 2], m.y, m.w); f[4 * kk + 3] = MODUL(f[4 * kk + 3], m.y, m.w);
            }
            keep(f);
            mbar_arrive_pred(xempty + (i & 3) * 8, l == 0);
          };
          auto publish = [&](int u, uint32_t (&f)[16]) {
#pragma unroll
            for (int kk = 0; kk < 4; kk++) stmatrix4(fa[kk] + OFF_STAGE + u * UNIT, f[4 * kk], f[4 * kk + 1], f[4 * kk + 2], f[4 * kk + 3]);
            if (zero == 0) fence_async_smem();
            __syncwarp();
            mbar_arrive_pred(bar_hpub + u * 8, l == 0);
          };
          auto multiply = [&](int i, uint32_t (&f)[16]) {
            mbar_wait(gfull + (i & 3) * 8, i >> 2);
            const uint64_t db = make_desc(base + (i & 3) * GST_BYTES + UNIT, 8192, 1024);
            wg_fence();
#pragma unroll
            for (int kk = 0; kk < 4; kk++) mma256_rs(ga, gb, f[4 * kk], f[4 * kk + 1], f[4 * kk + 2], f[4 * kk + 3], db + kk * 128);
            wg_commit();
          };
          auto next = [&](int i, uint32_t (&f)[16]) {
            wg_wait<1>();
            mbar_arrive_cl(rempty, GE + ((i + 2) & 3) * 8);
            uint32_t z = zero;
#pragma unroll
            for (int k = 0; k < 16; k += 2) asm volatile("lop3.b32 %0, %1, %2, %0, 0xA8;" : "+r"(z) : "r"(f[k]), "r"(f[k + 1]));
            fetch(i, f, z);
            normalize(f); modulate(i, f); multiply(i, f);
          };
          normalize(a[0]); normalize(a[1]);
          keep(a[0]); keep(a[1]);
          mbar_wait(bar_mod, 0);
          PROF(1, tid == 0, 2);
          modulate(0, a[0]); multiply(0, a[0]); publish(0, a[0]);
          modulate(1, a[1]); multiply(1, a[1]); publish(1, a[1]);
#pragma unroll 1
          for (int i = 2; i < NRS; i += 2) { next(i, a[0]); next(i + 1, a[1]); }
          wg_wait<1>();
          mbar_arrive_cl(rempty, GE + ((NRS + 2) & 3) * 8);
#pragma unroll 1
          for (int i = NRS; i < 14; i++) {
            mbar_wait(xfull + (i & 3) * 8, (i >> 2) & 1);
            mbar_wait(gfull + (i & 3) * 8, (i >> 2) & 1);
            const uint32_t xa = base + (i & 3) * GST_BYTES;
            const uint64_t da = make_desc(xa + wg * 8192, 16, 1024), db = make_desc(xa + UNIT, 8192, 1024);
            if (i == 13) bar_sync(2 + wg, 256);
            wg_fence();
#pragma unroll
            for (int kk = 0; kk < 4; kk++) mma256_ss(ga, gb, da + kk * 2, db + kk * 128, 1);
            wg_commit();
            if (i == 13) bar_arrive(3 - wg, 256);
            wg_wait<1>();
            uint32_t z = zero;
#pragma unroll
            for (int k = 0; k < 16; k += 2) asm volatile("lop3.b32 %0, %1, %2, %0, 0xA8;" : "+r"(z) : "r"(a[1][k]), "r"(a[1][k + 1]));
            mbar_arrive_cl(rempty, GE + ((i + 3) & 3) * 8 + z);
            mbar_arrive_pred(xempty + ((i + 3) & 3) * 8, l == 0 && i != NRS);
          }
          mbar_wait(xfull + 16, 1);
          wg_wait<0>();
          keep(ga); keep(gb);
#pragma unroll
          for (int i = 0; i < 64; i++) {
            asm volatile("mov.b32 %0, %1;" : "=f"(s[i]) : "f"(ga[i]));
            asm volatile("mov.b32 %0, %1;" : "=f"(o[i]) : "f"(gb[i]));
          }
        } else {
          float ga[64], gb[64];
#pragma unroll
          for (int i = 0; i < 64; i++) {
            asm volatile("mov.b32 %0, %1;" : "=f"(ga[i]) : "f"(s[i]));
            asm volatile("mov.b32 %0, %1;" : "=f"(gb[i]) : "f"(o[i]));
          }
#pragma unroll 1
          for (int i = 0; i < nst; i++) {
            mbar_wait(gfull + (i & 3) * 8, (i >> 2) & 1);
            const uint64_t da = make_desc(base + unit_of(xt, i & 3) + wg * 8192, 16, 1024), db = make_desc(base + unit_of(wt, i & 3), 8192, 1024);
            if (i == nst - 1) bar_sync(2 + wg, 256);
            wg_fence();
#pragma unroll
            for (int kk = 0; kk < 4; kk++) mma256_ss(ga, gb, da + kk * 2, db + kk * 128, kk ? 1 : i);
            wg_commit();
            if (i == nst - 1) bar_arrive(3 - wg, 256);
            wg_wait<1>();
            mbar_arrive_cl(rempty, GE + ((i + 3) & 3) * 8, i != 0);
            PROF(4, tid == 0 && (i & 3) == 0, 40 + (ps - 1) * 4 + i / 4);
          }
          wg_wait<0>();
          keep(ga); keep(gb);
#pragma unroll
          for (int i = 0; i < 64; i++) {
            asm volatile("mov.b32 %0, %1;" : "=f"(s[i]) : "f"(ga[i]));
            asm volatile("mov.b32 %0, %1;" : "=f"(o[i]) : "f"(gb[i]));
          }
        }
        mbar_arrive_cl(rempty, GE + (ps == 2 ? 24 : 8));
        if (ps == 2) break;
      }
      const uint32_t qw = base + wg * 8192, qt = QT >> (16 * ps), at = ps ? AT1 : AT0;
      {
        const uint32_t wt = ps ? WT1 : WT0;
        const uint64_t da0 = make_desc(qw + unit_of(qt, 2), 16, 1024), da1 = make_desc(qw + unit_of(qt, 3), 16, 1024);
        const uint64_t db0 = make_desc(base + unit_of(wt, 2), 8192, 1024), db1 = make_desc(base + unit_of(wt, 3), 8192, 1024);
        mbar_wait(gfull + 16, 1);
        bar_sync(2 + wg, 256);
        wg_fence();
#pragma unroll
        for (int kk = 0; kk < 4; kk++) mma_ss<1>(s, da0 + kk * 2, db0 + kk * 128, 1);
        wg_commit();
        mbar_wait(xfull + 24, 1);
        mbar_wait(gfull + 24, 1);
        wg_fence();
#pragma unroll
        for (int kk = 0; kk < 4; kk++) mma_ss<1>(s, da1 + kk * 2, db1 + kk * 128, 1);
        wg_commit();
        bar_arrive(3 - wg, 256);
        mbar_wait(ps == 0 ? bar_pread : bar_ofree + 8, 0);
        wg_wait<0>();
        keep(s);
        PROF(2, tid == 0, 8 + ps * 8);
        store_chunk<0>(s, qw + unit_of(qt, 0) + frag_offset(warp));
        store_chunk<1>(s, qw + unit_of(qt, 1) + frag_offset(warp));
        fence_async_smem();
        bar_sync(2 + wg, 256);
        wg_fence();
#pragma unroll
        for (int kk = 0; kk < 8; kk++) mma_ss<1>(o, (kk < 4 ? da0 : da1) + (kk & 3) * 2, (kk < 4 ? db0 : db1) + UNIT / 16 + (kk & 3) * 128, 1);
        wg_commit();
        mbar_wait(bfull, 0);
        wg_fence();
        issue_qk(s, qw + unit_of(qt, 0), qw + unit_of(qt, 1), base + unit_of(at, 0));
        wg_commit();
        bar_arrive(3 - wg, 256);
        wg_wait<1>();
        keep(o);
        mbar_arrive_cl(rempty, GE + 16);
        mbar_arrive_cl(rempty, GE + 24);
        store_chunk<0>(o, qw + unit_of(qt, 2) + frag_offset(warp));
        store_chunk<1>(o, qw + unit_of(qt, 3) + frag_offset(warp));
        wg_wait<0>();
        keep(s);
        mbar_arrive_cl(rempty, 0);
      }
      PROF(4, tid == 0 && ps == 1, 61);
      float l0 = 0.f, l1 = 0.f;
      auto step = [&](auto odd_c, const int j, uint32_t (&pw)[32], uint32_t (&pr)[32]) {
        constexpr bool ODD = decltype(odd_c)::value;
        const bool first = !ODD && (j & 2) == 0, last = ODD && j == 7;
        const uint32_t ph = (j >> 1) & 1;
        float i0, i1, a0, a1;
        const bool so = !ODD && j == 4;
        if (so) { i0 = inv_quad_sum(l0); i1 = inv_quad_sum(l1); l0 = 0.f; l1 = 0.f; }
        bool redo = !ODD && (j | ps) == 0;
        while (true) {
          if (redo) {
            float m0 = fmaxf(s[0], s[1]), m1 = fmaxf(s[2], s[3]);
#pragma unroll
            for (int i = 1; i < 16; i++) { m0 = fmaxf(m0, fmaxf(s[4 * i], s[4 * i + 1])); m1 = fmaxf(m1, fmaxf(s[4 * i + 2], s[4 * i + 3])); }
            m0 = fmaxf(m0, __shfl_xor_sync(0xffffffffu, m0, 1)); m1 = fmaxf(m1, __shfl_xor_sync(0xffffffffu, m1, 1));
            m0 = fmaxf(m0, __shfl_xor_sync(0xffffffffu, m0, 2)); m1 = fmaxf(m1, __shfl_xor_sync(0xffffffffu, m1, 2));
            m0 *= SCL2; m1 *= SCL2;
            if (!first) {
              m0 = fmaxf(m0, f0); m1 = fmaxf(m1, f1);
              const float c0 = ex2(f0 - m0), c1 = ex2(f1 - m1);
              l0 *= c0; l1 *= c1;
              wg_wait<0>();
              keep(o);
#pragma unroll
              for (int i = 0; i < 16; i++) { o[4 * i] *= c0; o[4 * i + 1] *= c0; o[4 * i + 2] *= c1; o[4 * i + 3] *= c1; }
            }
            f0 = m0; f1 = m1;
          }
          float b0 = 0.f, b1 = 0.f;
          a0 = 0.f; a1 = 0.f;
#pragma unroll
          for (int i = 0; i < 16; i++) {
            const float e0 = ex2(fmaf(s[4 * i], SCL2, -f0)), e1 = ex2(fmaf(s[4 * i + 1], SCL2, -f0));
            const float e2 = ex2(fmaf(s[4 * i + 2], SCL2, -f1)), e3 = ex2(fmaf(s[4 * i + 3], SCL2, -f1));
            a0 += e0; b0 += e1; a1 += e2; b1 += e3;
            pw[2 * i] = pack_bf(e0, e1); pw[2 * i + 1] = pack_bf(e2, e3);
            if (i == VREL) {
#pragma unroll
              for (int k = 0; k < 2 * VREL + 2; k++) asm volatile("" : "+r"(pw[k])::"memory");
              mbar_wait(bar_mod, 0);
              wg_wait<0>();
              mbar_arrive_cl(rempty, ODD ? 16 : 0, !redo && (ODD || j));
#pragma unroll
              for (int k = 4 * VREL + 4; k < 64; k++) asm volatile("" : "+f"(s[k])::"memory");
            }
          }
          a0 += b0; a1 += b1;
          if (redo) break;
          redo = __any_sync(0xffffffffu, !(a0 + a1 < 0x1p70f));
          if (first) {
            uint32_t m0 = __ballot_sync(0xffffffffu, a0 > 0x1p-50f), m1 = __ballot_sync(0xffffffffu, a1 > 0x1p-50f);
            m0 |= m0 >> 1; m1 |= m1 >> 1; m0 |= m0 >> 2; m1 |= m1 >> 2;
            redo = redo || (m0 & m1 & 0x11111111u) != 0x11111111u;
          }
          if (!redo) break;
        }
        l0 += a0; l1 += a1;
        keep(pw);
        keep(o);
        if (so) store_chunk<0>(o, i0, i1, qw + unit_of(qt, 0) + frag_offset(warp));
        keep(o);
        if (ODD && !(j & 2)) { fence_async_smem(); mbar_arrive_pred(bar_ofull + wg * 8, j > 4); }
        mbar_wait(bfull + (ODD ? 24 : 8), ph);
        bar_sync(2 + wg, 256);
        if (!last) {
          const uint32_t qn = qt >> (j >= 3 ? 8 : 0);
          wg_fence();
          issue_qk(s, qw + unit_of(qn, 0), qw + unit_of(qn, 1), base + unit_of(at, ODD ? 3 : 1));
          wg_commit();
          mbar_wait(bfull + (ODD ? 0 : 16), ODD ? ph ^ 1 : ph);
        }
        if (so) { store_chunk<1>(o, i0, i1, qw + unit_of(qt, 1) + frag_offset(warp)); keep(o); }
        wg_fence();
        issue_pv(o, pw, base + unit_of(at, ODD ? (last ? 3 : 0) : 2), !first);
        wg_commit();
        bar_arrive(3 - wg, 256);
        wg_wait<1>();
        keep(s);
        mbar_arrive_cl(rempty, ODD ? 24 : 8, !last);
        PROF(4, tid == 0 && ps == 1, 51 + j);
      };
      uint32_t pa[32], pb[32];
#pragma unroll 1
      for (int j = 0; j < 8; j += 2) {
        step(std::false_type{}, j, pa, pb);
        step(std::true_type{}, j + 1, pb, pa);
      }
      {
        const float i0 = inv_quad_sum(l0), i1 = inv_quad_sum(l1);
        wg_wait<0>();
        keep(o);
        mbar_arrive_cl(rempty, 24);
        store_chunk<0>(o, i0, i1, qw + unit_of(qt, 2) + frag_offset(warp));
        store_chunk<1>(o, i0, i1, qw + unit_of(qt, 3) + frag_offset(warp));
        fence_async_smem();
        mbar_arrive(bar_ofull + 16 + wg * 8);
      }
      PROF(2, tid == 0, 10 + ps * 8);
    }

    const int ln = fresh_lane(), g = ln >> 2, tq = ln & 3, ct = warp * 32 + ln;
    const bool lane0 = ln == 0;
    const int lrow0 = warp * 16 + g;
    const int grow0 = rb * 128 + lrow0;
    const uint32_t res = base + OFF_RES, trow = res + wg * 8192 + frag_offset(warp);
    uint32_t xr[32];
    uint4 sv[4], own;
    uint32_t* sp[4];
#pragma unroll
    for (int k = 0; k < 4; k++) sp[k] = g_stats + ((((tq >> 1) * 4 + k) ^ cj) * SEQ + grow0 + (tq & 1) * 8) * 4;
    {
      const uint64_t da = make_desc(base + wg * 8192, 16, 1024), db = make_desc(base, 8192, 1024);
      constexpr int U = UNIT / 16;
#define HALF_STAGE(acc, xu, wu) _Pragma("unroll") for (int kk = 0; kk < 4; kk++) mma_ss<1>(acc, da + (xu) * U + kk * 2, db + (wu) * U + kk * 128, 1)
      PROF(10, ct == PT, 19); STAMP(0);
      cluster_arrive();
      mbar_wait(gfull, 1);
      mbar_wait(gfull + 8, 1);
      bar_sync(2 + wg, 256);
      wg_fence();
      HALF_STAGE(o, 7, 1);
      HALF_STAGE(o, 8, 3);
      wg_commit();
      STAMP(16);
      mbar_wait(gfull + 16, 1);
      STAMP(17);
      wg_fence();
      HALF_STAGE(o, 6, 11);
      wg_commit();
      bar_arrive(3 - wg, 256);
      mbar_wait(bar_par, 0);
      uint32_t* xo = g_xch + ((size_t)b * 8 * 256 + ct) * 4;
      const uint32_t* xi = g_xch + ((size_t)(b ^ 2) * 8 * 256 + ct) * 4;
      const uint32_t par1 = (~lds1(par + PAR_CONST + 4) & 1) << 16;
      uint32_t ga[16];
      uint4 bw[8];
#define LOAD_PAR _Pragma("unroll") for (int i = 0; i < 8; i++) {                                                               \
        ga[2 * i] = lds1(par + PAR_T2 + i * 128 + tq * 16 + 12); ga[2 * i + 1] = lds1(par + PAR_T2 + i * 128 + 64 + tq * 16 + 12); \
        bw[i] = lds4(par + PAR_T1 + i * 64 + tq * 16);                                                                          \
        if (!(g & 1)) { bw[i].x = 0x3f803f80u; bw[i].y = 0x3f803f80u; }                                                         \
      }
      if (PPOS == 0) LOAD_PAR
      wg_wait<1>();
      mbar_arrive_pred(bar_rel, lane0);
      wg_wait<0>();
      keep(o);
      mbar_arrive_pred(bar_ring, lane0);
      PROF(8, ct == PT, 20); STAMP(1);
#define SEND(i) st_b128(xo + (i) * 1024, (pack_bf(o[8 * (i)], o[8 * (i) + 1]) & ~0x10000u) | par1, pack_bf(o[8 * (i) + 2], o[8 * (i) + 3]), \
                        pack_bf(o[8 * (i) + 4], o[8 * (i) + 5]), pack_bf(o[8 * (i) + 6], o[8 * (i) + 7]))
#pragma unroll
      for (int i = 0; i < NS1; i++) SEND(i);
      PROF(8, ct == PT, 21); STAMP(2);
      bar_sync(2 + wg, 256);
      wg_fence();
      HALF_STAGE(s, 7, 0);
      HALF_STAGE(s, 8, 2);
      HALF_STAGE(s, 6, 10);
      wg_commit();
      bar_arrive(3 - wg, 256);
      STAMP(18);
      mbar_wait(gfull + 24, 1);
#pragma unroll
      for (int i = NS1; i < 8; i++) SEND(i);
      uint4 v[8];
#pragma unroll
      for (int i = 0; i < 4; i++) v[i] = ld_b128(xi + i * 1024);
      if (PPOS == 1) LOAD_PAR
      STAMP(19);
      mbar_wait(bar_xres, 0);
      wg_wait<0>();
      mbar_arrive_pred(bar_ring + 8, lane0);
      bar_sync(2 + wg, 256);
      STAMP(20);
#pragma unroll
      for (int i = 4; i < 8; i++) v[i] = ld_b128(xi + i * 1024);
      mbar_wait(bar_xres, 0);
      wg_fence();
      HALF_STAGE(s, 9, 4);
      wg_commit();
      mbar_wait(bar_rx, 0);
      wg_fence();
      HALF_STAGE(s, 1, 5);
      wg_commit();
      bar_arrive(3 - wg, 256);
      STAMP(21);
      wg_wait<0>();
      keep(s);
      mbar_arrive_pred(bar_ring + 16, lane0);
      PROF(10, ct == PT, 23); STAMP(4);
#pragma unroll
      for (int i = 0; i < 16; i += 2) ldmatrix4((trow ^ ((i & 7) << 4)) + (i >> 3) * 16384, xr[2 * i], xr[2 * i + 1], xr[2 * i + 2], xr[2 * i + 3]);
      if (PPOS == 2) LOAD_PAR
      uint32_t pk[32];
      pack_p(s, pk);
      keep(pk);
      {
        uint32_t n = 0, miss;
        do {
          miss = 0;
#pragma unroll
          for (int i = 0; i < 8; i++) miss |= v[i].x ^ par1;
          miss = __any_sync(0xffffffffu, miss & 0x10000u);
          if (miss) {
#pragma unroll
            for (int i = 0; i < 8; i++)
              asm volatile("{ .reg .pred p; .reg .b32 t; xor.b32 t, %0, %5; and.b32 t, t, 0x10000; setp.ne.u32 p, t, 0;\n"
                           "@p ld.relaxed.gpu.global.v4.u32 {%0, %1, %2, %3}, [%4]; }"
                           : "+r"(v[i].x), "+r"(v[i].y), "+r"(v[i].z), "+r"(v[i].w) : "l"(xi + i * 1024), "r"(par1) : "memory");
          }
          watchdog(n);
        } while (miss);
      }
      PROF(8, ct == PT, 22); STAMP(3);
#pragma unroll
      for (int k = 0; k < 4; k++) sv[k] = ESV ? ld_b128(sp[k]) : make_uint4(0, 0, 0, 0);
      float ds[4] = {0.f, 0.f, 0.f, 0.f}, dl[4] = {0.f, 0.f, 0.f, 0.f}, q0[4] = {0.f, 0.f, 0.f, 0.f}, q1[4] = {0.f, 0.f, 0.f, 0.f};
#pragma unroll
      for (int i = 0; i < 8; i++) {
        const uint32_t u0 = hfma2(ga[2 * i], hadd2(pk[4 * i], v[i].x & ~0x10000u), xr[4 * i]);
        const uint32_t u1 = hfma2(ga[2 * i], hadd2(pk[4 * i + 1], v[i].y), xr[4 * i + 1]);
        const uint32_t u2 = hfma2(ga[2 * i + 1], hadd2(pk[4 * i + 2], v[i].z), xr[4 * i + 2]);
        const uint32_t u3 = hfma2(ga[2 * i + 1], hadd2(pk[4 * i + 3], v[i].w), xr[4 * i + 3]);
        xr[4 * i] = u0; xr[4 * i + 1] = u1; xr[4 * i + 2] = u2; xr[4 * i + 3] = u3;
        mma16816(ds, u0, u1, u2, u3, bw[i].x, bw[i].y);
        mma16816(dl, u0, u1, u2, u3, bw[i].z, bw[i].w);
        mma16816(q0, u0, u1, u2, u3, u0, u2);
        mma16816(q1, u0, u1, u2, u3, u1, u3);
      }
      const float sqa = __shfl_sync(0xffffffffu, (g & 1) ? q0[1] : q0[0], g * 4 + (g >> 1));
      const float sqb = __shfl_sync(0xffffffffu, (g & 1) ? q1[3] : q1[2], g * 4 + (g >> 1));
      own = (tq & 1) ? make_uint4(__float_as_uint(ds[2]), __float_as_uint(sqb), __float_as_uint(ds[3] + dl[3]), tag)
                                 : make_uint4(__float_as_uint(ds[0]), __float_as_uint(sqa), __float_as_uint(ds[1] + dl[1]), tag);
      if (tq < 2) st_b128(sp[0], own.x, own.y, own.z, own.w);
    }
    PROF(8, ct == PT, 29); STAMP(5);
    uint32_t mm, ih, il;
    float rbest;
    uint32_t wf[128];
    const uint32_t frow = (ln & 7) + (ln >> 4) * 8;
    const uint32_t wfo = base + (warp & 1) * 8192 + frow * 64 + ((((ln >> 3) & 1) ^ ((frow >> 1) & 3)) << 4);
#define LOAD_WF(m) _Pragma("unroll") for (int f = 0; f < 16; f++) {                                                   \
      const int r = ((f >> 1) * 4 + (m) * 2 + (f & 1)) * 4;                                                           \
      ldmatrix4t(((wfo + unit_of((m) ? FT_U : FT_G, warp >> 1)) ^ ((f & 1) * 32)) + (f >> 1) * 1024, wf[r], wf[r + 1], wf[r + 2], wf[r + 3]); \
    }
    bool early, wait1;
    {
#pragma unroll
      for (int i = 0; i < 16; i += 2) stmatrix4((trow ^ ((i & 7) << 4)) + (i >> 3) * 16384, xr[2 * i], xr[2 * i + 1], xr[2 * i + 2], xr[2 * i + 3]);
      const uint4 cst = lds4(par + PAR_CONST);
      const float A1 = __uint_as_float(cst.x), A2 = __uint_as_float(cst.z);
      uint32_t n = 0;
      early = false; wait1 = false;
#pragma unroll 1
      while (true) {
        uint32_t miss;
        asm volatile("{ .reg .pred p0, p1, p2, p3; .reg .b64 u, v; .reg .b128 w;\n"
                     "setp.ge.u32 p0, %22, 2; setp.ne.and.u32 p0, %4, %21, p0; setp.ne.u32 p1, %8, %21; setp.ne.u32 p2, %12, %21; setp.ne.u32 p3, %16, %21;\n"
                     "@p0 ld.relaxed.gpu.global.v4.u32 {%1, %2, %3, %4}, [%17];\n"
                     "@p1 ld.relaxed.gpu.global.v4.u32 {%5, %6, %7, %8}, [%18];\n"
                     "@p2 ld.relaxed.gpu.global.v4.u32 {%9, %10, %11, %12}, [%19];\n"
                     "@p3 ld.relaxed.gpu.global.v4.u32 {%13, %14, %15, %16}, [%20];\n"
                     "or.pred p0, p0, p1; or.pred p2, p2, p3; or.pred p0, p0, p2; vote.sync.any.pred p0, p0, 0xffffffff; selp.u32 %0, 1, 0, p0; }"
                     : "=r"(miss), "+r"(sv[0].x), "+r"(sv[0].y), "+r"(sv[0].z), "+r"(sv[0].w), "+r"(sv[1].x), "+r"(sv[1].y), "+r"(sv[1].z), "+r"(sv[1].w),
                       "+r"(sv[2].x), "+r"(sv[2].y), "+r"(sv[2].z), "+r"(sv[2].w), "+r"(sv[3].x), "+r"(sv[3].y), "+r"(sv[3].z), "+r"(sv[3].w)
                     : "l"(sp[0]), "l"(sp[1]), "l"(sp[2]), "l"(sp[3]), "r"(tag), "r"(tq) : "memory");
        if (!miss) break;
        wait1 = true;
        if (!early && (b >= NFFN || __all_sync(0xffffffffu, mbar_test(bar_box + (warp >> 1) * 8, 0)))) {
          early = true;
          LOAD_WF(0);
          __syncwarp();
          mbar_arrive_pred(bar_gate, lane0);
        }
        watchdog(n);
      }
      const uint4 v0 = tq < 2 ? own : sv[0], v1 = sv[1], v2 = sv[2], v3 = sv[3];
      PROF(8, ct == PT, 30); STAMP(6);
      float su = (__uint_as_float(v0.x) + __uint_as_float(v1.x)) + (__uint_as_float(v2.x) + __uint_as_float(v3.x));
      float sq = (__uint_as_float(v0.y) + __uint_as_float(v1.y)) + (__uint_as_float(v2.y) + __uint_as_float(v3.y));
      float dt = (__uint_as_float(v0.z) + __uint_as_float(v1.z)) + (__uint_as_float(v2.z) + __uint_as_float(v3.z));
      su += __shfl_xor_sync(0xffffffffu, su, 2); sq += __shfl_xor_sync(0xffffffffu, sq, 2); dt += __shfl_xor_sync(0xffffffffu, dt, 2);
      const float m = su * (1.f / DM);
      float mb, sd;
      ln_scalars(m, fmaxf(sq * (1.f / DM) - m * m, 0.f), mb, sd);
      const float inv = rcp(sd);
      rbest = (dt - mb * A1) * inv + A2;
      mm = pack_bf(mb, mb);
      ih = pack_bf(inv, inv);
      const float lo = inv - bf_lo(ih);
      il = pack_bf(lo, lo);
    }
    int ibest;
    {
      const uint32_t bits = __float_as_uint(rbest);
      const uint32_t key = (((int)bits < 0 ? ~bits : bits | 0x80000000u) & ~0x1ffu) | ((127 - lrow0 - (tq & 1) * 8) << 2) | tag;
      sts1(par + PAR_RED + warp * 4, __reduce_max_sync(0xffffffffu, key));
      PROF(8, ct == PT, 38); STAMP(7);
      uint32_t waited;
      asm volatile("{ .reg .pred p, q; setp.ne.u32 p, %1, 0; barrier.cta.red.or.pred q, 1, 256, p; selp.u32 %0, 1, 0, q; }" : "=r"(waited) : "r"((uint32_t)(wait1 && (wg || CW0))) : "memory");
      const uint4 ka = lds4(par + PAR_RED), kb = lds4(par + PAR_RED + 16);
      const uint32_t k2 = max(max(max(ka.x, ka.y), max(ka.z, ka.w)), max(max(kb.x, kb.y), max(kb.z, kb.w)));
      if (ct == 0 && ((cj & CWM) == 0 || (CWL && !waited))) st_relaxed(g_cand + rb, k2);
      ibest = 127 - ((k2 >> 2) & 127);
    }
    PROF(8, ct == PT, 39); STAMP(8);
    if ((ibest >> 4) == warp) {
      const int src = (ibest & 7) * 4 + ((ibest >> 3) & 1), ch = g * 2;
      const uint32_t cm = __shfl_sync(0xffffffffu, mm, src), ch_ = __shfl_sync(0xffffffffu, ih, src), cl = __shfl_sync(0xffffffffu, il, src);
      const uint32_t xa = res + (ch >> 3) * 16384 + ibest * 128 + (((ch & 7) ^ (ibest & 7)) << 4) + tq * 4;
      const uint32_t x0 = lds1(xa), x1 = lds1(xa ^ 16);
      const uint2 p0 = lds2(par + PAR_T2 + ch * 64 + tq * 16), p1 = lds2(par + PAR_T2 + ch * 64 + 64 + tq * 16);
      uint32_t* dst = g_row + rb * 2 * DM + cj * 128 + ln * 4;
      st_pairs(dst, ln_mod(x0, cm, ch_, cl, p0.x, p0.y), ln_mod(x1, cm, ch_, cl, p1.x, p1.y), tag);
      st_pairs(dst + DM, x0, x1, tag);
      __syncwarp();
    }
    PROF(8, ct == PT, 37); STAMP(9);
    uint32_t wd[64];
    const uint32_t wda = base + unit_of(FT_D, warp >> 1) + (warp & 1) * 8192 + frow * 128 + ((((ln >> 3) & 1) ^ (ln & 7)) << 4);
#define LOAD_WD(f) ldmatrix4t((wda ^ ((((f) >> 1) & 3) * 32)) + ((f) >> 3) * 4096 + ((f) & 1) * 2048, wd[4 * (f)], wd[4 * (f) + 1], wd[4 * (f) + 2], wd[4 * (f) + 3])
    if (!early) {
      if (b < NFFN) mbar_wait(bar_box + (warp >> 1) * 8, 0);
      LOAD_WF(0);
      __syncwarp();
      mbar_arrive_pred(bar_gate, lane0);
    }
    if (b < NFFN) {
      const uint32_t own = base + unit_of(FT_G, warp >> 1) + (warp & 1) * 8192;
      mbar_wait(bar_box + (4 + (warp >> 1)) * 8, 0);
      LOAD_WF(1);
      uint32_t* const ydst = g_ypart + ((size_t)(warp * 16 + tq * 2) * NFFN + b) * 8 + g;
      PROF(8, ct == PT, 31); STAMP(10);
      mbar_wait(bar_box + (8 + (warp >> 1)) * 8, 0);
#pragma unroll
      for (int f = 0; f < WDE; f++) LOAD_WD(f);
      STAMP(11);
      mbar_wait(bar_sel, 0);
      PROF(8, ct == PT, 33); STAMP(12);
      float d[8][4];
#pragma unroll
      for (int i = 0; i < 4; i++) { d[i][0] = 0.f; d[i][1] = 0.f; d[i][2] = 0.f; d[i][3] = 0.f; }
#pragma unroll
      for (int ks = 0; ks < 8; ks++) {
        const uint2 hb = lds2(own + 256 + ks * 32 + tq * 8);
#pragma unroll
        for (int mt = 0; mt < 4; mt++) {
          const int r = ks * 16 + mt * 4;
          mma16816(d[mt], wf[r], wf[r + 1], wf[r + 2], wf[r + 3], hb.x, hb.y);
        }
      }
      sts2(own + (tq * 8 + g) * 8, __float_as_uint((tq & 2) ? ((tq & 1) ? d[1][2] : d[1][0]) : ((tq & 1) ? d[0][2] : d[0][0])),
           __float_as_uint((tq & 2) ? ((tq & 1) ? d[3][2] : d[3][0]) : ((tq & 1) ? d[2][2] : d[2][0])));
      bar_sync(1, 256);
      uint32_t ab[4];
      {
        float G = 0.f, U = 0.f;
        uint2 pv[8];
#pragma unroll
        for (int w8 = 0; w8 < 8; w8++) pv[w8] = lds2(base + ln * 8 + ((FT_G >> (w8 >> 1) * 4) & 15) * UNIT + (w8 & 1) * 8192);
#pragma unroll
        for (int w8 = 0; w8 < 8; w8 += 2) {
          G += __uint_as_float(pv[w8].x) + __uint_as_float(pv[w8 + 1].x);
          U += __uint_as_float(pv[w8].y) + __uint_as_float(pv[w8 + 1].y);
        }
#pragma unroll
        for (int f = WDE; f < 16; f++) LOAD_WD(f);
        const float act = rbf(silu_f(rbf(G))) * rbf(U);
        const uint32_t pk = pack_bf(act, __shfl_down_sync(0xffffffffu, act, 1));
#pragma unroll
        for (int i = 0; i < 4; i++) ab[i] = __shfl_sync(0xffffffffu, pk, i * 8 + tq * 2);
      }
      PROF(8, ct == PT, 34); STAMP(13);
#pragma unroll
      for (int mt = 0; mt < 8; mt++) {
        d[mt][0] = 0.f; d[mt][1] = 0.f; d[mt][2] = 0.f; d[mt][3] = 0.f;
        mma16816(d[mt], wd[mt * 8], wd[mt * 8 + 1], wd[mt * 8 + 2], wd[mt * 8 + 3], ab[0], ab[1]);
        mma16816(d[mt], wd[mt * 8 + 4], wd[mt * 8 + 5], wd[mt * 8 + 6], wd[mt * 8 + 7], ab[2], ab[3]);
      }
#pragma unroll
      for (int i = 0; i < 4; i++) {
        const int m4 = (i >> 1) * 4, e = (i & 1) * 2;
        const float y = (tq & 2) ? ((tq & 1) ? d[m4 + 3][e] : d[m4 + 2][e]) : ((tq & 1) ? d[m4 + 1][e] : d[m4][e]);
        st_relaxed(ydst + (m4 * 2 + (i & 1)) * NFFN * 8, tagf(y, tag));
      }
      PROF(8, ct == PT, 35); STAMP(14);
    }
    mbar_wait(bar_sel, 0);
    mbar_arrive_pred(bar_win, ct == 0);
    const int iwin = lds1(par + PAR_CONST + 60) & 0x7ff;
    const bool cand = (iwin >> 4) == rb * 8 + warp;
    {
      const uint32_t mm0 = __shfl_sync(0xffffffffu, mm, ln & ~1), mm1 = __shfl_sync(0xffffffffu, mm, ln | 1);
      const uint32_t ih0 = __shfl_sync(0xffffffffu, ih, ln & ~1), ih1 = __shfl_sync(0xffffffffu, ih, ln | 1);
      const uint32_t il0 = __shfl_sync(0xffffffffu, il, ln & ~1), il1 = __shfl_sync(0xffffffffu, il, ln | 1);
#pragma unroll 1
      for (int hf = 0; hf < 2; hf++) {
        uint32_t x[16];
#pragma unroll
        for (int i = 0; i < 8; i += 2) ldmatrix4((trow ^ (i << 4)) + hf * 16384, x[2 * i], x[2 * i + 1], x[2 * i + 2], x[2 * i + 3]);
#pragma unroll
        for (int i = 0; i < 8; i++) {
          const uint4 pv = lds4(par + PAR_T2 + (hf * 8 + i) * 64 + tq * 16);
          x[2 * i] = hadd2(x[2 * i], hmul2(pv.z, ln_mod(x[2 * i], mm0, ih0, il0, pv.x, pv.y)));
          x[2 * i + 1] = hadd2(x[2 * i + 1], hmul2(pv.z, ln_mod(x[2 * i + 1], mm1, ih1, il1, pv.x, pv.y)));
        }
#pragma unroll
        for (int i = 0; i < 8; i += 2) stmatrix4((trow ^ (i << 4)) + hf * 16384, x[2 * i], x[2 * i + 1], x[2 * i + 2], x[2 * i + 3]);
      }
      if (!cand) fence_async_smem();
      __syncwarp();
      if (!cand && elect_one()) {
        tma2d_store(&maps.out, res + warp * 2048, cj * 128, rb * 128 + warp * 16);
        tma2d_store(&maps.out, res + 16384 + warp * 2048, cj * 128 + 64, rb * 128 + warp * 16);
        asm volatile("cp.async.bulk.commit_group;" ::: "memory");
      }
    }
    if (cand) {
      const int wrow0 = warp * 16;
#pragma unroll 2
      for (int p = 0; p < 8; p++) {
        const int row = 2 * p + (ln >> 4), ch = ln & 15;
        const uint4 v = lds4(res + (ch >> 3) * 16384 + (wrow0 + row) * 128 + (((ch & 7) ^ (row & 7)) << 4));
        if (rb * 128 + wrow0 + row != iwin) *reinterpret_cast<uint4*>(P.out + (size_t)(rb * 128 + wrow0 + row) * DM + cj * 128 + ch * 8) = v;
      }
    }
    asm volatile("cp.async.bulk.wait_group.read 0;" ::: "memory");
    PROF(8, ct == PT, 11); STAMP(15);
    cluster_wait();
  }
}

typedef CUresult (*EncodeFn)(CUtensorMap*, CUtensorMapDataType, cuuint32_t, void*, const cuuint64_t*, const cuuint64_t*,
                             const cuuint32_t*, const cuuint32_t*, CUtensorMapInterleave, CUtensorMapSwizzle,
                             CUtensorMapL2promotion, CUtensorMapFloatOOBfill);

void map2d(EncodeFn enc, CUtensorMap* m, const void* p, uint64_t rows, uint64_t cols, uint32_t brows) {
  cuuint64_t dims[2] = {cols, rows}, strides[1] = {cols * 2};
  cuuint32_t box[2] = {64, brows}, es[2] = {1, 1};
  enc(m, CU_TENSOR_MAP_DATA_TYPE_BFLOAT16, 2, const_cast<void*>(p), dims, strides, box, es, CU_TENSOR_MAP_INTERLEAVE_NONE,
      CU_TENSOR_MAP_SWIZZLE_128B, CU_TENSOR_MAP_L2_PROMOTION_L2_256B, CU_TENSOR_MAP_FLOAT_OOB_FILL_NONE);
}
void map2d_narrow(EncodeFn enc, CUtensorMap* m, const void* p, uint64_t rows, uint64_t cols, uint32_t brows) {
  cuuint64_t dims[2] = {cols, rows}, strides[1] = {cols * 2};
  cuuint32_t box[2] = {32, brows}, es[2] = {1, 1};
  enc(m, CU_TENSOR_MAP_DATA_TYPE_BFLOAT16, 2, const_cast<void*>(p), dims, strides, box, es, CU_TENSOR_MAP_INTERLEAVE_NONE,
      CU_TENSOR_MAP_SWIZZLE_64B, CU_TENSOR_MAP_L2_PROMOTION_L2_64B, CU_TENSOR_MAP_FLOAT_OOB_FILL_NONE);
}
void map3d(EncodeFn enc, CUtensorMap* m, const void* p, uint64_t rows, uint64_t cols, uint32_t brows, uint32_t nch) {
  cuuint64_t dims[3] = {64, rows, cols / 64}, strides[2] = {cols * 2, 128};
  cuuint32_t box[3] = {64, brows, nch}, es[3] = {1, 1, 1};
  enc(m, CU_TENSOR_MAP_DATA_TYPE_BFLOAT16, 3, const_cast<void*>(p), dims, strides, box, es, CU_TENSOR_MAP_INTERLEAVE_NONE,
      CU_TENSOR_MAP_SWIZZLE_128B, CU_TENSOR_MAP_L2_PROMOTION_L2_256B, CU_TENSOR_MAP_FLOAT_OOB_FILL_NONE);
}

}

extern "C" void kernel_launch(void* const* d_in, const int* in_sizes, int n_in, void* d_out, int out_size) {
  (void)in_sizes; (void)n_in; (void)out_size;
  static EncodeFn enc = nullptr;
  if (!enc) {
    void* fn = nullptr;
    cudaDriverEntryPointQueryResult st;
    cudaGetDriverEntryPoint("cuTensorMapEncodeTiled", &fn, cudaEnableDefault, &st);
    enc = (EncodeFn)fn;
    cudaFuncSetAttribute(fused_kernel, cudaFuncAttributeMaxDynamicSharedMemorySize, SMEM_BYTES);
  }
  Maps maps;
  map2d(enc, &maps.x, d_in[0], SEQ, DM, 128);
  map2d(enc, &maps.out, d_out, SEQ, DM, 16);
  map3d(enc, &maps.wq, d_in[3], DM, NQ, 64, 2);
  map3d(enc, &maps.k, d_in[1], 4 * SK, 128, 128, 1);
  map3d(enc, &maps.v, d_in[2], 4 * SK, 128, 128, 1);
  map3d(enc, &maps.wo, d_in[4], NQ, DM, 64, 2);
  map2d_narrow(enc, &maps.wg, d_in[7], DM, FF, 256);
  map2d_narrow(enc, &maps.wu, d_in[8], DM, FF, 256);
  map3d(enc, &maps.wd, d_in[9], FF, DM, 32, 4);
  map2d_narrow(enc, &maps.wm, d_in[11], DM, NMOD, 256);
  Ptrs p;
  p.x = (const __nv_bfloat16*)d_in[0];
  p.w_r = (const __nv_bfloat16*)d_in[6];
  p.w_gate = (const __nv_bfloat16*)d_in[7];
  p.w_up = (const __nv_bfloat16*)d_in[8];
  p.w_down = (const __nv_bfloat16*)d_in[9];
  p.c = (const __nv_bfloat16*)d_in[10];
  p.w_mod = (const __nv_bfloat16*)d_in[11];
  p.out = (__nv_bfloat16*)d_out;
  fused_kernel<<<NMAIN + NHELP, 384, SMEM_BYTES>>>(maps, p);
}
```

```cpp
#include <cuda_runtime.h>
#include <cuda_bf16.h>
#include <cuda.h>
#include <stdint.h>
#include <type_traits>

#define HD 2
#define HDX 2
#define NRS 8
#define FPACE 3
#define GOST 20
#define WB 2
#define WN 20
#define RES0 17
#define RES1 20
#define HU 32
#define NS1 6
#define PG0 15
#define PSL 0
#define CWM 7
#define WDE 16
#define CWL 1
#define CW0 0
#define ESV 1
#define PPOS 1
#define FB0 0
#define FB2 8
#define OPS 8192
#define OFL 0
#define ODS 8
#define MODUL hfma2
#define ODS1 5
#define VREL 5
#define E0 3

namespace {

constexpr int SEQ = 2048, DM = 1024, NQ = 4096, SK = 2048, WIN = 512, FF = 3584, NMOD = 6144;
constexpr int NMAIN = 128, NHELP = 4, NFFN = 112;
constexpr int NSLOT = 4, SLOT_BYTES = 32768, UNIT = 16384, GST_BYTES = 3 * UNIT;
constexpr uint32_t XT1 = 0xDCBA, XT2 = 0x9687;
constexpr uint32_t WT0 = 0xA741, WT1 = 0x7420, WT2 = 0x4A20;
constexpr uint32_t AT0 = WT1, AT1 = WT2;
constexpr uint32_t QT = 0xDC9696DC;
constexpr int OFF_STAGE = 12 * UNIT;
constexpr uint32_t FT_G = 0x07B3, FT_U = 0xA628, FT_D = 0x5149;
constexpr int OFF_RES = 12 * UNIT;
constexpr int OFF_PAR = 14 * UNIT;
constexpr int OFF_BAR = OFF_PAR + 2528;
constexpr int SMEM_BYTES = OFF_BAR + 544;
static_assert(SMEM_BYTES <= 232448, "smem");

constexpr int PAR_T1 = 0;
constexpr int PAR_T2 = 512;
constexpr int PAR_CONST = 1536;
constexpr int PAR_RED = 1600;
constexpr int PAR_SINK = 2176;

struct Maps {
  CUtensorMap x, wq, k, v, wo, wg, wu, wd, wm, out;
};
struct Ptrs {
  const __nv_bfloat16 *x, *w_r, *c, *w_mod, *w_gate, *w_up, *w_down;
  __nv_bfloat16* out;
};

__device__ __align__(1024) uint8_t g_act[16 * 80 * UNIT];
__device__ __align__(128) uint32_t g_mod[NMOD];
__device__ __align__(128) uint32_t g_modp[2 * 2 * DM];
__device__ __align__(128) uint32_t g_ln1[SEQ * 4];
__device__ __align__(128) uint32_t g_cnt_h[16 * 32];
__device__ __align__(128) uint32_t g_cnt_o[128 * 32];
__device__ __align__(128) uint32_t g_xch[NMAIN * 8 * 256 * 4];
__device__ __align__(128) uint32_t g_stats[8 * SEQ * 4];
__device__ __align__(128) uint32_t g_cand[32];
__device__ __align__(128) uint32_t g_row[16 * 2 * DM];
__device__ __align__(128) uint32_t g_ypart[NMAIN * NFFN * 8];
__device__ uint32_t g_epoch;

__device__ __forceinline__ uint32_t fresh_lane() { uint32_t l; asm volatile("mov.u32 %0, %%laneid;" : "=r"(l)); return l; }
__device__ __forceinline__ uint32_t frag_offset(int warp) {
  const uint32_t l = fresh_lane();
  return ((warp & 3) * 16 + (l & 15)) * 128 + (((l >> 4) ^ (l & 7)) << 4);
}
__device__ __forceinline__ bool elect_one() {
  uint32_t p;
  asm volatile("{ .reg .pred q; elect.sync _|q, 0xffffffff; selp.u32 %0, 1, 0, q; }" : "=r"(p));
  return p;
}
__device__ __forceinline__ uint32_t smem_u32(const void* p) { return (uint32_t)__cvta_generic_to_shared(p); }
__device__ __forceinline__ void mbar_init(uint32_t bar, uint32_t cnt) {
  asm volatile("mbarrier.init.shared::cta.b64 [%0], %1;" ::"r"(bar), "r"(cnt) : "memory");
}
__device__ __forceinline__ void mbar_expect_tx(uint32_t bar, uint32_t bytes) {
  asm volatile("mbarrier.arrive.expect_tx.shared::cta.b64 _, [%0], %1;" ::"r"(bar), "r"(bytes) : "memory");
}
__device__ __forceinline__ void mbar_arrive(uint32_t bar) {
  asm volatile("mbarrier.arrive.shared::cta.b64 _, [%0];" ::"r"(bar) : "memory");
}
__device__ __forceinline__ void mbar_arrive_pred(uint32_t bar, bool p) {
  asm volatile("{ .reg .pred p; setp.ne.b32 p, %1, 0; @p mbarrier.arrive.shared::cta.b64 _, [%0]; }" ::"r"(bar), "r"((int)p) : "memory");
}
__device__ __forceinline__ void mbar_arrive_cl(uint32_t bar, uint32_t off, bool p = true) {
  asm volatile("{ .reg .pred p, q; .reg .b32 a; setp.ne.b32 q, %2, 0; setp.ne.and.b32 p, %0, 0, q; add.u32 a, %0, %1; @p mbarrier.arrive.shared::cluster.b64 _, [a]; }"
               ::"r"(bar), "r"(off), "r"((int)p) : "memory");
}
__device__ __forceinline__ uint32_t mapa(uint32_t addr, uint32_t cta) {
  uint32_t r; asm("mapa.shared::cluster.u32 %0, %1, %2;" : "=r"(r) : "r"(addr), "r"(cta)); return r;
}
__device__ __forceinline__ void cluster_arrive() { asm volatile("barrier.cluster.arrive.relaxed.aligned;" ::: "memory"); }
__device__ __forceinline__ void cluster_wait() { asm volatile("barrier.cluster.wait.aligned;" ::: "memory"); }
__device__ __forceinline__ void watchdog(uint32_t& n) {
}
__device__ __forceinline__ void mbar_wait(uint32_t bar, uint32_t parity) {
  asm volatile("{\n.reg .pred p;\nWAIT_%=:\nmbarrier.try_wait.parity.shared::cta.b64 p, [%0], %1;\n@!p bra WAIT_%=;\n}" ::"r"(bar), "r"(parity) : "memory");
}
__device__ __forceinline__ bool mbar_test(uint32_t bar, uint32_t parity) {
  uint32_t ok;
  asm volatile("{\n.reg .pred p;\nmbarrier.test_wait.parity.shared::cta.b64 p, [%1], %2;\nselp.u32 %0, 1, 0, p;\n}" : "=r"(ok) : "r"(bar), "r"(parity) : "memory");
  return ok;
}
__device__ __forceinline__ uint64_t l2_stream() {
  uint64_t f; asm("createpolicy.fractional.L2::evict_first.b64 %0, 1.0;" : "=l"(f)); return f;
}
__device__ __forceinline__ void tma2d(uint32_t dst, const CUtensorMap* m, int c0, int c1, uint32_t bar) {
  asm volatile("cp.async.bulk.tensor.2d.shared::cluster.global.mbarrier::complete_tx::bytes.L2::cache_hint [%0], [%1, {%3, %4}], [%2], %5;"
               ::"r"(dst), "l"(m), "r"(bar), "r"(c0), "r"(c1), "l"(l2_stream()) : "memory");
}
__device__ __forceinline__ void bulk_load(uint32_t dst, const void* src, uint32_t bytes, uint32_t bar) {
  asm volatile("cp.async.bulk.shared::cluster.global.mbarrier::complete_tx::bytes [%0], [%1], %2, [%3];" ::"r"(dst), "l"(src), "r"(bytes), "r"(bar) : "memory");
}
__device__ __forceinline__ void bulk_load_stream(uint32_t dst, const void* src, uint32_t bytes, uint32_t bar) {
  asm volatile("cp.async.bulk.shared::cluster.global.mbarrier::complete_tx::bytes.L2::cache_hint [%0], [%1], %2, [%3], %4;"
               ::"r"(dst), "l"(src), "r"(bytes), "r"(bar), "l"(l2_stream()) : "memory");
}
__device__ __forceinline__ void tma2d_store(const CUtensorMap* m, uint32_t src, int c0, int c1) {
  asm volatile("cp.async.bulk.tensor.2d.global.shared::cta.bulk_group [%0, {%2, %3}], [%1];" ::"l"(m), "r"(src), "r"(c0), "r"(c1) : "memory");
}
__device__ __forceinline__ void bulk_store(void* dst, uint32_t src, uint32_t bytes) {
  asm volatile("cp.async.bulk.global.shared::cta.bulk_group [%0], [%1], %2;" ::"l"(dst), "r"(src), "r"(bytes) : "memory");
}
__device__ __forceinline__ uint32_t unit_of(uint32_t table, uint32_t i) { return ((table >> (i * 4)) & 15) * UNIT; }
__device__ __forceinline__ void tma3d(uint32_t dst, const CUtensorMap* m, int c0, int c1, int c2, uint32_t bar) {
  asm volatile("cp.async.bulk.tensor.3d.shared::cluster.global.mbarrier::complete_tx::bytes.L2::cache_hint [%0], [%1, {%3, %4, %5}], [%2], %6;"
               ::"r"(dst), "l"(m), "r"(bar), "r"(c0), "r"(c1), "r"(c2), "l"(l2_stream()) : "memory");
}
template <bool STREAM>
__device__ __forceinline__ void tma3d_mc(uint32_t dst, const CUtensorMap* m, int c0, int c1, int c2, uint32_t bar) {
  if (STREAM)
    asm volatile("cp.async.bulk.tensor.3d.shared::cluster.global.mbarrier::complete_tx::bytes.multicast::cluster.L2::cache_hint [%0], [%1, {%3, %4, %5}], [%2], %6, %7;"
                 ::"r"(dst), "l"(m), "r"(bar), "r"(c0), "r"(c1), "r"(c2), "h"((uint16_t)3), "l"(l2_stream()) : "memory");
  else
    asm volatile("cp.async.bulk.tensor.3d.shared::cluster.global.mbarrier::complete_tx::bytes.multicast::cluster [%0], [%1, {%3, %4, %5}], [%2], %6;"
                 ::"r"(dst), "l"(m), "r"(bar), "r"(c0), "r"(c1), "r"(c2), "h"((uint16_t)3) : "memory");
}
__device__ __forceinline__ void prefetch_map(const CUtensorMap* m) {
  asm volatile("prefetch.tensormap [%0];" ::"l"(m) : "memory");
}
__device__ __forceinline__ void fence_async() { asm volatile("fence.proxy.async.global;" ::: "memory"); }
__device__ __forceinline__ void fence_async_smem() { asm volatile("fence.proxy.async.shared::cta;" ::: "memory"); }
__device__ __forceinline__ void bar_sync(int id, int n) { asm volatile("bar.sync %0, %1;" ::"r"(id), "r"(n) : "memory"); }
__device__ __forceinline__ void bar_arrive(int id, int n) { asm volatile("bar.arrive %0, %1;" ::"r"(id), "r"(n) : "memory"); }
__device__ __forceinline__ void wg_fence() { asm volatile("wgmma.fence.sync.aligned;" ::: "memory"); }
__device__ __forceinline__ void wg_commit() { asm volatile("wgmma.commit_group.sync.aligned;" ::: "memory"); }
template <int N> __device__ __forceinline__ void wg_wait() { asm volatile("wgmma.wait_group.sync.aligned %0;" ::"n"(N) : "memory"); }
__device__ __forceinline__ uint64_t make_desc(uint32_t addr, uint32_t lbo, uint32_t sbo) {
  return (uint64_t)((addr & 0x3FFFF) >> 4) | ((uint64_t)(lbo >> 4) << 16) | ((uint64_t)(sbo >> 4) << 32) | (1ull << 62);
}
__device__ __forceinline__ uint32_t ld_relaxed(const uint32_t* p) {
  uint32_t v; asm volatile("ld.relaxed.gpu.global.u32 %0, [%1];" : "=r"(v) : "l"(p) : "memory"); return v;
}
__device__ __forceinline__ uint32_t ld_acquire(const uint32_t* p) {
  uint32_t v; asm volatile("ld.acquire.gpu.global.u32 %0, [%1];" : "=r"(v) : "l"(p) : "memory"); return v;
}
__device__ __forceinline__ uint4 ld_relaxed4(const uint32_t* p) {
  uint4 v; asm volatile("ld.relaxed.gpu.global.v4.u32 {%0,%1,%2,%3}, [%4];" : "=r"(v.x), "=r"(v.y), "=r"(v.z), "=r"(v.w) : "l"(p) : "memory"); return v;
}
__device__ __forceinline__ uint2 ld_relaxed2(const uint32_t* p) {
  uint2 v; asm volatile("ld.relaxed.gpu.global.v2.u32 {%0,%1}, [%2];" : "=r"(v.x), "=r"(v.y) : "l"(p) : "memory"); return v;
}
__device__ __forceinline__ void st_relaxed(uint32_t* p, uint32_t v) {
  asm volatile("st.relaxed.gpu.global.u32 [%0], %1;" ::"l"(p), "r"(v) : "memory");
}
__device__ __forceinline__ void st_relaxed2(uint32_t* p, uint32_t a, uint32_t b) {
  asm volatile("st.relaxed.gpu.global.v2.u32 [%0], {%1,%2};" ::"l"(p), "r"(a), "r"(b) : "memory");
}
__device__ __forceinline__ void st_relaxed4(uint32_t* p, uint32_t a, uint32_t b, uint32_t c, uint32_t d) {
  asm volatile("st.relaxed.gpu.global.v4.u32 [%0], {%1,%2,%3,%4};" ::"l"(p), "r"(a), "r"(b), "r"(c), "r"(d) : "memory");
}
__device__ __forceinline__ void st_b128(uint32_t* p, uint32_t a, uint32_t b, uint32_t c, uint32_t d) {
  asm volatile("{ .reg .b64 u, v; .reg .b128 w; mov.b64 u, {%1, %2}; mov.b64 v, {%3, %4}; mov.b128 w, {u, v}; st.relaxed.gpu.global.b128 [%0], w; }"
               ::"l"(p), "r"(a), "r"(b), "r"(c), "r"(d) : "memory");
}
__device__ __forceinline__ uint4 ld_b128(const uint32_t* p) {
  uint4 r;
  asm volatile("{ .reg .b64 u, v; .reg .b128 w; ld.relaxed.gpu.global.b128 w, [%4]; mov.b128 {u, v}, w; mov.b64 {%0, %1}, u; mov.b64 {%2, %3}, v; }"
               : "=r"(r.x), "=r"(r.y), "=r"(r.z), "=r"(r.w) : "l"(p) : "memory");
  return r;
}
__device__ __forceinline__ void st_pairs(uint32_t* p, uint32_t a, uint32_t b, uint32_t tag) {
  asm volatile("{ .reg .b64 u, v; mov.b64 u, {%1, %3}; mov.b64 v, {%2, %3}; st.relaxed.gpu.global.v2.b64 [%0], {u, v}; }"
               ::"l"(p), "r"(a), "r"(b), "r"(tag) : "memory");
}
__device__ __forceinline__ uint4 ld_pairs(const uint32_t* p) {
  uint4 v;
  asm volatile("{ .reg .b64 u, v; ld.relaxed.gpu.global.v2.b64 {u, v}, [%4]; mov.b64 {%0, %1}, u; mov.b64 {%2, %3}, v; }"
               : "=r"(v.x), "=r"(v.y), "=r"(v.z), "=r"(v.w) : "l"(p) : "memory");
  return v;
}
__device__ __forceinline__ uint2 ld_pair(const uint32_t* p) {
  uint2 v;
  asm volatile("{ .reg .b64 u; ld.relaxed.gpu.global.b64 u, [%2]; mov.b64 {%0, %1}, u; }" : "=r"(v.x), "=r"(v.y) : "l"(p) : "memory");
  return v;
}
__device__ __forceinline__ void red_release(uint32_t* p, uint32_t v) {
  asm volatile("red.release.gpu.global.add.u32 [%0], %1;" ::"l"(p), "r"(v) : "memory");
}
__device__ __forceinline__ uint32_t ldg_nc1(const void* p) {
  uint32_t v;
  asm volatile("ld.global.nc.u32 %0, [%1];" : "=r"(v) : "l"(p));
  return v;
}
__device__ __forceinline__ uint4 ldg_nc4(const void* p) {
  uint4 v; asm volatile("ld.global.nc.L1::no_allocate.v4.u32 {%0,%1,%2,%3}, [%4];" : "=r"(v.x), "=r"(v.y), "=r"(v.z), "=r"(v.w) : "l"(p)); return v;
}
__device__ __forceinline__ uint4 ldg_stream4(const void* p) {
  uint4 v;
  asm volatile("ld.global.nc.L1::no_allocate.L2::cache_hint.v4.u32 {%0,%1,%2,%3}, [%4], %5;" : "=r"(v.x), "=r"(v.y), "=r"(v.z), "=r"(v.w) : "l"(p), "l"(l2_stream()));
  return v;
}
__device__ __forceinline__ void stg4(void* p, uint4 v) {
  asm volatile("st.global.v4.u32 [%0], {%1,%2,%3,%4};" ::"l"(p), "r"(v.x), "r"(v.y), "r"(v.z), "r"(v.w) : "memory");
}
__device__ __forceinline__ void wait_counter(const uint32_t* p, uint32_t target) {
  uint32_t n = 0;
  while (__any_sync(0xffffffffu, (int)(ld_acquire(p) - target) < 0)) { watchdog(n); }
}
__device__ __forceinline__ uint32_t tagf(float v, uint32_t tag) { return (__float_as_uint(v) & ~3u) | tag; }
__device__ __forceinline__ bool tag_ok(uint4 v, uint32_t tag) { return (((v.x ^ tag) | (v.y ^ tag) | (v.z ^ tag) | (v.w ^ tag)) & 3u) == 0; }
__device__ __forceinline__ float untag_sum(uint32_t a, uint32_t b) { return __uint_as_float(a & ~3u) + __uint_as_float(b & ~3u); }
__device__ __forceinline__ uint4 poll4(const uint32_t* p, uint32_t tag) {
  uint4 v = ld_relaxed4(p);
  uint32_t n = 0;
  while (!__all_sync(0xffffffffu, tag_ok(v, tag))) { v = ld_relaxed4(p); watchdog(n); }
  return v;
}
__device__ __forceinline__ float bf_lo(uint32_t v) { return __uint_as_float(v << 16); }
__device__ __forceinline__ float bf_hi(uint32_t v) { return __uint_as_float(v & 0xffff0000u); }
__device__ __forceinline__ uint32_t pack_bf(float lo, float hi) {
  uint32_t r; asm("cvt.rn.bf16x2.f32 %0, %1, %2;" : "=r"(r) : "f"(hi), "f"(lo)); return r;
}
__device__ __forceinline__ float rbf(float v) { return __uint_as_float(pack_bf(0.f, v) & 0xffff0000u); }
__device__ __forceinline__ uint32_t hmul2(uint32_t a, uint32_t b) {
  uint32_t r; asm("mul.rn.bf16x2 %0, %1, %2;" : "=r"(r) : "r"(a), "r"(b)); return r;
}
__device__ __forceinline__ uint32_t hadd2(uint32_t a, uint32_t b) {
  uint32_t r; asm("add.rn.bf16x2 %0, %1, %2;" : "=r"(r) : "r"(a), "r"(b)); return r;
}
__device__ __forceinline__ uint32_t hsub2(uint32_t a, uint32_t b) {
  uint32_t r; asm("sub.rn.bf16x2 %0, %1, %2;" : "=r"(r) : "r"(a), "r"(b)); return r;
}
__device__ __forceinline__ uint32_t hmax2(uint32_t a, uint32_t b) {
  uint32_t r; asm("max.bf16x2 %0, %1, %2;" : "=r"(r) : "r"(a), "r"(b)); return r;
}
__device__ __forceinline__ float rcp(float x) { float r; asm("rcp.approx.ftz.f32 %0, %1;" : "=f"(r) : "f"(x)); return r; }
__device__ __forceinline__ float ex2(float x) { float r; asm("ex2.approx.ftz.f32 %0, %1;" : "=f"(r) : "f"(x)); return r; }
__device__ __forceinline__ void stmatrix4(uint32_t addr, uint32_t a, uint32_t b, uint32_t c, uint32_t d) {
  asm volatile("stmatrix.sync.aligned.m8n8.x4.shared.b16 [%0], {%1,%2,%3,%4};" ::"r"(addr), "r"(a), "r"(b), "r"(c), "r"(d) : "memory");
}
__device__ __forceinline__ void ldmatrix4(uint32_t addr, uint32_t& a, uint32_t& b, uint32_t& c, uint32_t& d) {
  asm volatile("ldmatrix.sync.aligned.m8n8.x4.shared.b16 {%0,%1,%2,%3}, [%4];" : "=r"(a), "=r"(b), "=r"(c), "=r"(d) : "r"(addr) : "memory");
}
__device__ __forceinline__ void ldmatrix4t(uint32_t addr, uint32_t& a, uint32_t& b, uint32_t& c, uint32_t& d) {
  asm volatile("ldmatrix.sync.aligned.m8n8.x4.trans.shared.b16 {%0,%1,%2,%3}, [%4];" : "=r"(a), "=r"(b), "=r"(c), "=r"(d) : "r"(addr) : "memory");
}
__device__ __forceinline__ void mma16816(float (&d)[4], uint32_t a0, uint32_t a1, uint32_t a2, uint32_t a3, uint32_t b0, uint32_t b1) {
  asm volatile("mma.sync.aligned.m16n8k16.row.col.f32.bf16.bf16.f32 {%0,%1,%2,%3}, {%4,%5,%6,%7}, {%8,%9}, {%0,%1,%2,%3};"
               : "+f"(d[0]), "+f"(d[1]), "+f"(d[2]), "+f"(d[3]) : "r"(a0), "r"(a1), "r"(a2), "r"(a3), "r"(b0), "r"(b1));
}
__device__ __forceinline__ void sts1(uint32_t a, uint32_t v) { asm volatile("st.shared.u32 [%0], %1;" ::"r"(a), "r"(v) : "memory"); }
__device__ __forceinline__ uint4 lds4(uint32_t a) {
  uint4 v; asm volatile("ld.shared.v4.u32 {%0,%1,%2,%3}, [%4];" : "=r"(v.x), "=r"(v.y), "=r"(v.z), "=r"(v.w) : "r"(a) : "memory"); return v;
}
__device__ __forceinline__ uint2 lds2(uint32_t a) {
  uint2 v; asm volatile("ld.shared.v2.u32 {%0,%1}, [%2];" : "=r"(v.x), "=r"(v.y) : "r"(a) : "memory"); return v;
}
__device__ __forceinline__ uint32_t lds1(uint32_t a) {
  uint32_t v; asm volatile("ld.shared.u32 %0, [%1];" : "=r"(v) : "r"(a) : "memory"); return v;
}
__device__ __forceinline__ void sts2(uint32_t a, uint32_t x, uint32_t y) { asm volatile("st.shared.v2.u32 [%0], {%1,%2};" ::"r"(a), "r"(x), "r"(y) : "memory"); }
__device__ __forceinline__ void sts4(uint32_t a, uint4 v) {
  asm volatile("st.shared.v4.u32 [%0], {%1,%2,%3,%4};" ::"r"(a), "r"(v.x), "r"(v.y), "r"(v.z), "r"(v.w) : "memory");
}
__device__ __forceinline__ float silu_f(float v) { return __fdividef(v, 1.f + __expf(-v)); }
__device__ __forceinline__ uint32_t hfma2(uint32_t a, uint32_t b, uint32_t c) {
  uint32_t r; asm("fma.rn.bf16x2 %0, %1, %2, %3;" : "=r"(r) : "r"(a), "r"(b), "r"(c)); return r;
}
__device__ __forceinline__ void split_inv(float sd, uint32_t& ih, uint32_t& il) {
  const float inv = rcp(sd);
  ih = pack_bf(inv, inv);
  const float lo = inv - bf_lo(ih);
  il = pack_bf(lo, lo);
}
__device__ __forceinline__ uint32_t ln_norm(uint32_t x, uint32_t mean2, uint32_t ih, uint32_t il) {
  const uint32_t d = hsub2(x, mean2);
  return hfma2(d, ih, hmul2(d, il));
}
__device__ __forceinline__ uint32_t modul(uint32_t n, uint32_t c1, uint32_t sh) { return hadd2(hmul2(n, c1), sh); }
__device__ __forceinline__ uint32_t ln_mod(uint32_t x, uint32_t mean2, uint32_t ih, uint32_t il, uint32_t c1, uint32_t sh) {
  return modul(ln_norm(x, mean2, ih, il), c1, sh);
}

#define R8(a, i) "+f"(a[i]), "+f"(a[i + 1]), "+f"(a[i + 2]), "+f"(a[i + 3]), "+f"(a[i + 4]), "+f"(a[i + 5]), "+f"(a[i + 6]), "+f"(a[i + 7])
#define D64 "{%0,%1,%2,%3,%4,%5,%6,%7,%8,%9,%10,%11,%12,%13,%14,%15,%16,%17,%18,%19,%20,%21,%22,%23,%24,%25,%26,%27,%28,%29,%30,%31," \
            "%32,%33,%34,%35,%36,%37,%38,%39,%40,%41,%42,%43,%44,%45,%46,%47,%48,%49,%50,%51,%52,%53,%54,%55,%56,%57,%58,%59,%60,%61,%62,%63}"
template <int TB>
__device__ __forceinline__ void mma_ss(float (&d)[64], uint64_t da, uint64_t db, int sc) {
  asm volatile("{\n.reg .pred p;\nsetp.ne.b32 p, %66, 0;\n"
               "wgmma.mma_async.sync.aligned.m64n128k16.f32.bf16.bf16 " D64 ", %64, %65, p, 1, 1, 0, %67;\n}"
               : R8(d, 0), R8(d, 8), R8(d, 16), R8(d, 24), R8(d, 32), R8(d, 40), R8(d, 48), R8(d, 56)
               : "l"(da), "l"(db), "r"(sc), "n"(TB));
}
template <int TB>
__device__ __forceinline__ void mma_rs(float (&d)[64], uint32_t a0, uint32_t a1, uint32_t a2, uint32_t a3, uint64_t db, int sc) {
  asm volatile("{\n.reg .pred p;\nsetp.ne.b32 p, %69, 0;\n"
               "wgmma.mma_async.sync.aligned.m64n128k16.f32.bf16.bf16 " D64 ", {%64,%65,%66,%67}, %68, p, 1, 1, %70;\n}"
               : R8(d, 0), R8(d, 8), R8(d, 16), R8(d, 24), R8(d, 32), R8(d, 40), R8(d, 48), R8(d, 56)
               : "r"(a0), "r"(a1), "r"(a2), "r"(a3), "l"(db), "r"(sc), "n"(TB));
}
#define D128 "{%0,%1,%2,%3,%4,%5,%6,%7,%8,%9,%10,%11,%12,%13,%14,%15,%16,%17,%18,%19,%20,%21,%22,%23,%24,%25,%26,%27,%28,%29,%30,%31," \
             "%32,%33,%34,%35,%36,%37,%38,%39,%40,%41,%42,%43,%44,%45,%46,%47,%48,%49,%50,%51,%52,%53,%54,%55,%56,%57,%58,%59,%60,%61,%62,%63," \
             "%64,%65,%66,%67,%68,%69,%70,%71,%72,%73,%74,%75,%76,%77,%78,%79,%80,%81,%82,%83,%84,%85,%86,%87,%88,%89,%90,%91,%92,%93,%94,%95," \
             "%96,%97,%98,%99,%100,%101,%102,%103,%104,%105,%106,%107,%108,%109,%110,%111,%112,%113,%114,%115,%116,%117,%118,%119,%120,%121,%122,%123,%124,%125,%126,%127}"
#define R128(d, e) R8(d, 0), R8(d, 8), R8(d, 16), R8(d, 24), R8(d, 32), R8(d, 40), R8(d, 48), R8(d, 56), \
                   R8(e, 0), R8(e, 8), R8(e, 16), R8(e, 24), R8(e, 32), R8(e, 40), R8(e, 48), R8(e, 56)
__device__ __forceinline__ void mma256_ss(float (&d)[64], float (&e)[64], uint64_t da, uint64_t db, int sc) {
  asm volatile("{\n.reg .pred p;\nsetp.ne.b32 p, %130, 0;\n"
               "wgmma.mma_async.sync.aligned.m64n256k16.f32.bf16.bf16 " D128 ", %128, %129, p, 1, 1, 0, 1;\n}"
               : R128(d, e) : "l"(da), "l"(db), "r"(sc));
}
__device__ __forceinline__ void mma256_rs(float (&d)[64], float (&e)[64], uint32_t a0, uint32_t a1, uint32_t a2, uint32_t a3, uint64_t db) {
  asm volatile("{\n.reg .pred p;\nsetp.ne.b32 p, 1, 0;\n"
               "wgmma.mma_async.sync.aligned.m64n256k16.f32.bf16.bf16 " D128 ", {%128,%129,%130,%131}, %132, p, 1, 1, 1;\n}"
               : R128(d, e) : "r"(a0), "r"(a1), "r"(a2), "r"(a3), "l"(db));
}
template <int N> __device__ __forceinline__ void keep(float (&a)[N]) {
#pragma unroll
  for (int i = 0; i < N; i++) asm volatile("" : "+f"(a[i])::"memory");
}
template <int N> __device__ __forceinline__ void keep(uint32_t (&a)[N]) {
#pragma unroll
  for (int i = 0; i < N; i++) asm volatile("" : "+r"(a[i])::"memory");
}

#define STAMP(idx) do {} while (0)
#define PROF(grp, cond, idx) do {} while (0)

constexpr float SCL2 = 1.4426950408889634f * 0.08838834764831845f;

__device__ __forceinline__ void pack_p(const float (&s)[64], uint32_t (&p)[32]) {
#pragma unroll
  for (int i = 0; i < 32; i++) p[i] = pack_bf(s[2 * i], s[2 * i + 1]);
}

__device__ __forceinline__ void issue_qk(float (&s)[64], uint32_t q0, uint32_t q1, uint32_t kslot) {
  const uint64_t db = make_desc(kslot, 16, 1024), da0 = make_desc(q0, 16, 1024), da1 = make_desc(q1, 16, 1024);
#pragma unroll
  for (int kk = 0; kk < 8; kk++) mma_ss<0>(s, (kk < 4 ? da0 : da1) + (kk & 3) * 2, db + (kk >> 2) * 1024 + (kk & 3) * 2, kk != 0);
}
__device__ __forceinline__ void issue_pv(float (&o)[64], uint32_t (&p)[32], uint32_t vslot, int acc) {
  uint64_t db = make_desc(vslot, 16384, 1024);
#pragma unroll
  for (int kk = 0; kk < 8; kk++)
    mma_rs<1>(o, p[4 * kk], p[4 * kk + 1], p[4 * kk + 2], p[4 * kk + 3], db + kk * 128, kk == 0 ? acc : 1);
}

template <int H>
__device__ __forceinline__ void store_chunk(const float (&a)[64], uint32_t addr) {
#pragma unroll
  for (int i = 8 * H; i < 8 * H + 8; i += 2)
    stmatrix4(addr ^ ((i & 7) << 4), pack_bf(a[4 * i], a[4 * i + 1]), pack_bf(a[4 * i + 2], a[4 * i + 3]),
              pack_bf(a[4 * i + 4], a[4 * i + 5]), pack_bf(a[4 * i + 6], a[4 * i + 7]));
}
template <int H>
__device__ __forceinline__ void store_chunk(const float (&a)[64], float i0, float i1, uint32_t addr) {
#pragma unroll
  for (int i = 8 * H; i < 8 * H + 8; i += 2)
    stmatrix4(addr ^ ((i & 7) << 4), pack_bf(a[4 * i] * i0, a[4 * i + 1] * i0), pack_bf(a[4 * i + 2] * i1, a[4 * i + 3] * i1),
              pack_bf(a[4 * i + 4] * i0, a[4 * i + 5] * i0), pack_bf(a[4 * i + 6] * i1, a[4 * i + 7] * i1));
}
__device__ __forceinline__ float inv_quad_sum(float l) {
  l += __shfl_xor_sync(0xffffffffu, l, 1);
  l += __shfl_xor_sync(0xffffffffu, l, 2);
  return rcp(l);
}

__device__ __forceinline__ void ln_scalars(float mean, float var, float& mb, float& sd) {
  mb = rbf(mean);
  float r; asm("sqrt.approx.ftz.f32 %0, %1;" : "=f"(r) : "f"(rbf(rbf(var) + 1e-5f)));
  sd = rbf(r);
}

__global__ void __cluster_dims__(2, 1, 1) __launch_bounds__(384, 1) fused_kernel(const __grid_constant__ Maps maps, const Ptrs P) {
  extern __shared__ __align__(1024) uint8_t smem_raw[];
  const uint32_t base = smem_u32(smem_raw);
  const int tid = threadIdx.x, lane = tid & 31;
  const int warp = __shfl_sync(0xffffffffu, tid >> 5, 0);
  const int b = blockIdx.x;
  PROF(31, tid == 0, 0);

  if (b >= NMAIN) {
    float* sc = reinterpret_cast<float*>(smem_raw);
    float* red = sc + DM;
    for (int k = tid; k < DM; k += 384) sc[k] = rbf(silu_f(__bfloat162float(P.c[k])));
    __syncthreads();
    if (tid < 256) {
      const int col = 2048 + (b - NMAIN) * 1024 + (tid & 127) * 8, r0 = (tid >> 7) * 512;
      float acc[8];
#pragma unroll
      for (int e = 0; e < 8; e++) acc[e] = 0.f;
#pragma unroll 1
      for (int r = r0; r < r0 + 512; r += HU) {
        uint4 w[HU];
#pragma unroll
        for (int u = 0; u < HU; u++) w[u] = ldg_stream4(P.w_mod + (size_t)(r + u) * NMOD + col);
#pragma unroll
        for (int u = 0; u < HU; u++) {
          float s = sc[r + u];
          acc[0] += s * bf_lo(w[u].x); acc[1] += s * bf_hi(w[u].x); acc[2] += s * bf_lo(w[u].y); acc[3] += s * bf_hi(w[u].y);
          acc[4] += s * bf_lo(w[u].z); acc[5] += s * bf_hi(w[u].z); acc[6] += s * bf_lo(w[u].w); acc[7] += s * bf_hi(w[u].w);
        }
      }
      if (tid >= 128) {
#pragma unroll
        for (int e = 0; e < 8; e++) red[(tid & 127) * 8 + e] = acc[e];
      }
      const uint32_t tag = ld_relaxed(&g_epoch) % 3 + 1;
      bar_sync(1, 256);
      if (tid < 128) {
        uint32_t o[8];
#pragma unroll
        for (int e = 0; e < 8; e++) o[e] = __float_as_uint(rbf(acc[e] + red[tid * 8 + e])) | tag;
        st_relaxed4(g_mod + col, o[0], o[1], o[2], o[3]);
        st_relaxed4(g_mod + col + 4, o[4], o[5], o[6], o[7]);
        const uint4 wr = ldg_nc4(P.w_r + tid * 8);
        const uint32_t wv[4] = {wr.x, wr.y, wr.z, wr.w};
        float dsum = 0.f;
#pragma unroll
        for (int e = 0; e < 8; e++) {
          const float m = bf_hi(o[e]);
          dsum += (b == NMAIN + 2 ? rbf(1.f + m) : m) * ((e & 1) ? bf_hi(wv[e >> 1]) : bf_lo(wv[e >> 1]));
        }
#pragma unroll
        for (int k = 16; k > 0; k >>= 1) dsum += __shfl_xor_sync(0xffffffffu, dsum, k);
        if (lane == 0) st_relaxed(g_mod + (b - NMAIN) * 4 + warp, tagf(dsum, tag));
      }
    }
    PROF(2, tid == 0, 1);
    return;
  }

  const int rank = b & 1;
  const int rb = ((b >> 4) << 1) | rank, cj = (b >> 1) & 7;
  const uint32_t bfull = base + OFF_BAR, bempty = bfull + NSLOT * 8;
  const uint32_t gfull = bempty + NSLOT * 8, gempty = gfull + 32;
  const uint32_t bar_ofull = gempty + 32;
  const uint32_t bar_ofree = bar_ofull + 32;
  const uint32_t bar_par = bar_ofree + 32;
  const uint32_t bar_mod = bar_par + 8;
  const uint32_t bar_pread = bar_mod + 8;
  const uint32_t bar_xres = bar_pread + 8;
  const uint32_t bar_ring = bar_xres + 8;
  const uint32_t bar_box = bar_ring + 24;
  const uint32_t bar_go = bar_box + 96;
  const uint32_t bar_go2 = bar_go + 16;
  const uint32_t bar_cnt = bar_go + 24;
  const uint32_t xfull = bar_go + 40, xempty = xfull + 32;
  const uint32_t bar_hw = xempty + 32, bar_hx = bar_hw + 8;
  const uint32_t bar_hpub = bar_hx + 16;
  const uint32_t bar_win = bar_hpub + 16;
  const uint32_t bar_rx = bar_win + 8;
  const uint32_t bar_sel = bar_rx + 8;
  const uint32_t bar_gate = bar_sel + 8;
  const uint32_t bar_rel = bar_gate + 8;
  const uint32_t bar_od = bar_rel + 8;
  const uint32_t bar_res = bar_go + 8;
  const uint32_t stage = base + OFF_STAGE, par = base + OFF_PAR;

  if (warp == 8 && elect_one()) {
    for (int s = 0; s < NSLOT; s++) { mbar_init(bfull + s * 8, 1); mbar_init(bempty + s * 8, 16); }
    for (int s = 0; s < 4; s++) { mbar_init(gfull + s * 8, 1); mbar_init(gempty + s * 8, 16); mbar_init(xfull + s * 8, 1); mbar_init(xempty + s * 8, 8); mbar_init(bar_ofree + s * 8, 1); mbar_init(bar_ofull + s * 8, 128); }
    mbar_init(bar_par, 64); mbar_init(bar_mod, 256); mbar_init(bar_pread, 2); mbar_init(bar_xres, 1);
    mbar_init(bar_ring, 8); mbar_init(bar_ring + 8, 8); mbar_init(bar_ring + 16, 8);
    mbar_init(bar_go, 1); mbar_init(bar_go2, 1); mbar_init(bar_cnt, 1); mbar_init(bar_cnt + 8, 1); mbar_init(bar_hpub, 8); mbar_init(bar_hpub + 8, 8); mbar_init(bar_res, 1); mbar_init(bar_win, 1); mbar_init(bar_rx, 1); mbar_init(bar_sel, 64); mbar_init(bar_gate, 8); mbar_init(bar_rel, 8); mbar_init(bar_od, 1);
    for (int s = 0; s < 12; s++) mbar_init(bar_box + s * 8, 1);
    asm volatile("fence.mbarrier_init.release.cluster;" ::: "memory");
    prefetch_map(&maps.x); prefetch_map(&maps.wq); prefetch_map(&maps.k); prefetch_map(&maps.v);
  }
  if (warp == 9 && elect_one()) {
    mbar_init(bar_hw, 1); mbar_init(bar_hx, 1); mbar_init(bar_hx + 8, 1);
    asm volatile("fence.mbarrier_init.release.cluster;" ::: "memory");
    mbar_expect_tx(bar_hw, 32768);
    mbar_expect_tx(bar_hx, 16384);
    mbar_expect_tx(bar_hx + 8, 16384);
    const __nv_bfloat16* xs = P.x + (size_t)(rb * 128 + cj * 16) * DM;
    bulk_load(base + 2 * GST_BYTES, xs, 16384, bar_hx);
    tma2d(stage, &maps.wm, (b >> 1) * 32, rank * 512, bar_hw);
    tma2d(stage + 16384, &maps.wm, (b >> 1) * 32, rank * 512 + 256, bar_hw);
    bulk_load(base + 3 * GST_BYTES, xs + 8 * DM, 16384, bar_hx + 8);
  }
  cluster_arrive();

  if (warp >= 8) {
    asm volatile("setmaxnreg.dec.sync.aligned.u32 40;");
    if (warp < 10) bar_arrive(1, 320);
    const uint32_t epoch = ld_relaxed(&g_epoch);
    cluster_wait();
    if (warp == 8) {
      const int kvrow = (cj >> 1) * SK + (SK - WIN);
      int wch = cj * 8 + rank * 2;
#pragma unroll 1
      for (int ps = 0; ps < 3; ps++) {
        const CUtensorMap* mw = ps == 2 ? &maps.wo : &maps.wq;
        const uint32_t xt = ps == 1 ? XT1 : XT2, wt = ps == 0 ? WT0 : (ps == 1 ? WT1 : WT2);
        const int nst = ps == 2 ? 32 : 16;
#pragma unroll 1
        for (int i = 0; i < nst; i++) {
          const uint32_t bf = gfull + (i & 3) * 8;
          const int kt = ps == 2 ? (((cj & 1) * 4 + ((i >> 1) & 3)) * 4 + (i >> 3)) * 2 + (i & 1) : (i + (ps ? 0 : b & 14)) & 15;
          const uint32_t wd = base + unit_of(wt, i & 3) + rank * UNIT, xd = base + unit_of(xt, i & 3);
          const uint8_t* xs = g_act + (uint32_t)(rb * 80 + (ps - 1) * 16 + kt) * UNIT;
          if (ps == 0 && i == HD) mbar_wait(bar_mod, 0);
          const bool xfirst = ps && i < 2;
          if (ps == 2 && i == 0) mbar_wait(bar_ofree + 24, 0);
          if (i == 0) fence_async();
          mbar_wait(gempty + (i & 3) * 8, ((i >> 2) & 1) ^ 1);
          if (elect_one()) {
            mbar_expect_tx(bf, ps ? GST_BYTES : 2 * UNIT);
            if (xfirst) bulk_load_stream(xd, xs, UNIT, bf);
          }
          if (ps && i < 4) mbar_wait(bempty + i * 8, 1);
          if (elect_one()) tma3d_mc<true>(wd, mw, 0, (i == 31 ? kt ^ (rank * 32) : kt) * 64, i == 31 ? cj * 2 : wch, bf);
          if (ps) {
            if (i == 16 || i == 24) { mbar_wait(bar_cnt + i - 16, 0); fence_async(); }
            if (i == RES0) mbar_wait(bar_res, 0);
            if (i == 2) mbar_wait(bar_ofree + (ps - 1) * 16, 0);
            if (elect_one()) {
              if (i == 31) bulk_load(xd, xs, UNIT, bf); else if (!xfirst) bulk_load_stream(xd, xs, UNIT, bf);
              mbar_arrive_pred(bar_go, i == GOST - 1);
              if (PG0 < 16) mbar_arrive_pred(bar_go2, ps == 1 && i == PG0);
              mbar_arrive_pred(bar_od, i == (ps == 1 ? ODS1 : ODS));
              if (i == RES0) mbar_expect_tx(bar_xres, 32768);
              if (i == RES0 || i == RES1) tma2d(base + OFF_RES + (i == RES1) * UNIT, &maps.x, cj * 128 + (i == RES1) * 64, rb * 128, bar_xres);
            }
          }
        }
        if (ps == 2) break;
        wch = ps ? ((wch >> 3) ^ rank) * 2 : wch + 4;
#pragma unroll 1
        for (int u = 0; u < 16; u++) {
          const bool isk = (u == 0) || ((u & 1) && u < 15);
          const int blk = (isk ? (u + 1) >> 1 : (u == 15 ? 7 : (u >> 1) - 1)) & 3;
          const uint32_t sl = base + unit_of(ps ? AT1 : AT0, u & 3) + rank * UNIT, bf = bfull + (u & 3) * 8;
          if (u < 4) mbar_wait(gempty + ((u + 1) >> 1) * 8, 1);
          mbar_wait(bempty + (u & 3) * 8, ((u >> 2) & 1) ^ 1);
          if (elect_one()) {
            mbar_arrive_pred(bar_go2, ps && u + 16 == PG0);
            mbar_expect_tx(bf, SLOT_BYTES);
            tma3d_mc<false>(sl, isk ? &maps.k : &maps.v, 0, kvrow + blk * 128, rank, bf);
          }
        }
      }
      if (elect_one()) mbar_expect_tx(bar_rx, UNIT);
      mbar_wait(bar_rel, 0);
      if (elect_one()) {
        bulk_load_stream(base + UNIT, g_act + (uint32_t)(rb * 80 + 16 + 63 - (cj & 1) * 32) * UNIT, UNIT, bar_rx);
      }
      if (b < NFFN) {
#pragma unroll 1
        for (int u = 0; u < 12; u++) {
          const uint32_t dst = base + unit_of(u < 4 ? FT_G : (u < 8 ? FT_U : FT_D), u & 3);
          if (elect_one()) mbar_expect_tx(bar_box + u * 8, UNIT);
          if (u == FB0 || u == 2 || u == FB2) mbar_wait(bar_ring + (u == FB2 ? 16 : (u + 6) & 8), 0);
          if (u >= FPACE) mbar_wait(bar_box + (u - FPACE) * 8, 0);
          if (elect_one()) {
            if (u < 8) tma2d(dst, u < 4 ? &maps.wg : &maps.wu, b * 32, (u & 3) * 256, bar_box + u * 8);
            else tma3d(dst, &maps.wd, 0, b * 32, (u - 8) * 4, bar_box + u * 8);
          }
        }
      }
    } else if (warp == 9) {
      const uint32_t target = 8 * (epoch + 1);
      uint32_t hmask = 0;
#pragma unroll 1
      for (int i = 0; i < 16; i++) {
        if (i == HDX) mbar_wait(bar_mod, 0);
        const uint32_t need = i == 15 ? 0xffffu : 1u << ((2 * cj + i) & 15);
        if (i >= NRS && (hmask & need) != need) {
          uint32_t n = 0;
          do { hmask = __ballot_sync(0xffffffffu, ld_acquire(&g_cnt_h[rb * 32 + (lane & 15)]) == epoch + 1); watchdog(n); } while ((hmask & need) != need);
          PROF(1, lane == 0 && i == NRS, 26);
          fence_async();
        }
        mbar_wait(xempty + (i & 3) * 8, ((i >> 2) & 1) ^ 1);
        if (elect_one()) {
          mbar_expect_tx(xfull + (i & 3) * 8, UNIT);
          if (i < NRS) tma2d(base + (i & 3) * GST_BYTES, &maps.x, ((2 * cj + i) & 15) * 64, rb * 128, xfull + (i & 3) * 8);
          else bulk_load_stream(base + (i & 3) * GST_BYTES, g_act + (uint32_t)(rb * 80 + ((2 * cj + i) & 15)) * UNIT, UNIT, xfull + (i & 3) * 8);
        }
      }
      prefetch_map(&maps.wo);
#pragma unroll 1
      for (int t = 0; t < 4; t++) {
        if (t & 1) mbar_wait(bar_od, t >> 1);
#pragma unroll 1
        for (int p = 0; p < 32768 / OPS; p++) {
          const uint32_t w = p / (16384 / OPS), c = (p / (8192 / OPS)) & 1, off = w * 8192 + (p % (8192 / OPS)) * OPS;
          mbar_wait(bar_ofull + (t & 1) * 16 + w * 8, t >> 1);
          if (elect_one()) {
            bulk_store(g_act + (uint32_t)(rb * 80 + 16 + (cj * 4 + t) * 2 + c) * UNIT + off, base + unit_of(QT, 2 * t + c) + off, OPS);
            asm volatile("cp.async.bulk.commit_group;" ::: "memory");
            asm volatile("cp.async.bulk.wait_group.read %0;" ::"n"(OFL) : "memory");
          }
        }
        if (elect_one()) {
          asm volatile("cp.async.bulk.wait_group.read 0;" ::: "memory");
          mbar_arrive(t < 3 ? bar_ofree + t * 8 : bar_res);
          asm volatile("cp.async.bulk.wait_group 0;" ::: "memory");
          fence_async();
          red_release(&g_cnt_o[((rb * 4 + t) * 2 + (cj >> 2)) * 32], 2);
        }
        if (t) {
          wait_counter(&g_cnt_o[(rb * 8 + 2 * t + (cj & 1)) * 32], target);
          if (t & 1) wait_counter(&g_cnt_o[(rb * 8 + (t == 1 ? cj & 1 : 7 - (cj & 1))) * 32], target);
          if (elect_one()) mbar_arrive(t == 1 ? bar_ofree + 24 : bar_cnt + t * 8 - 16);
        }
      }
      PROF(2, lane == 0, 27);
      const uint32_t tag = epoch % 3 + 1;
      const uint32_t* inbox = g_cand + (lane & 15);
      mbar_wait(bar_ring + 16, 0);
      uint32_t c0 = ld_relaxed(inbox), n = 0;
#define CAND_STEP(cv)                                                                                        \
      {                                                                                                      \
        const bool valid = (cv & 3u) == tag, all = __all_sync(0xffffffffu, valid);                           \
        const uint32_t best = __reduce_max_sync(0xffffffffu, valid ? cv : 0u);                               \
        const uint32_t blk = __ffs(__ballot_sync(0xffffffffu, cv == best)) - 1;                              \
        if (best) sts2(par + PAR_CONST + 56, best, (blk << 7 | (~best >> 2 & 127)) | (all ? 0x1800 : 0x800)); \
        if (all) break;                                                                                      \
        cv = ld_relaxed(inbox);                                                                              \
      }
      while (true) { CAND_STEP(c0) watchdog(n); }
    } else {
      const int t2 = tid - 320;
      mbar_wait(bar_hpub + (warp & 1) * 8, 0);
      PROF(1, t2 == 0, 24);
#pragma unroll 1
      for (int c = 0; c < 8; c++) {
        const uint32_t off = (warp & 1) * UNIT + c * 2048 + lane * 16;
        uint8_t* dst = g_act + (uint32_t)(rb * 80 + cj * 2) * UNIT + off;
        const uint4 v0 = lds4(stage + off), v1 = lds4(stage + off + 512), v2 = lds4(stage + off + 1024), v3 = lds4(stage + off + 1536);
        stg4(dst, v0); stg4(dst + 512, v1); stg4(dst + 1024, v2); stg4(dst + 1536, v3);
      }
      __syncwarp();
      PROF(1, t2 == 0, 15);
      if (lane == 0) {
        mbar_arrive(bar_pread);
        red_release(&g_cnt_h[rb * 32 + cj * 2 + (warp & 1)], 1);
        PROF(1, t2 == 0, 25);
        prefetch_map(&maps.wg); prefetch_map(&maps.wu); prefetch_map(&maps.wd); prefetch_map(&maps.out);
      }
      __syncwarp();
      if (b < NFFN) {
        mbar_wait(bar_go2, 0);
        const __nv_bfloat16* pg = ((b & 1) ? P.w_up : P.w_gate) + (b >> 1) * 64 + (size_t)t2 * FF;
        const __nv_bfloat16* pd = P.w_down + (size_t)b * 32768 + t2 * 64;
        PROF(2, t2 == 0, 13);
#pragma unroll 1
        for (int i = 0; i < WN; i += WB) {
          uint32_t v[WB];
#pragma unroll
          for (int u = 0; u < WB; u++) {
            const int k = i + u;
            asm volatile("ld.global.cg.L2::128B.u32 %0, [%1];" : "=r"(v[u]) : "l"(k < 16 ? pg + (size_t)k * 64 * FF : pd + (k - 16) * 4096));
          }
#pragma unroll
          for (int u = 1; u < WB; u++) v[0] ^= v[u];
          sts1(par + PAR_SINK + t2 * 4, v[0]);
        }
        PROF(2, t2 == 0, 14);
      }
      const uint32_t tag = epoch % 3 + 1;
      mbar_wait(bar_go, 0);
      bar_sync(4, 64);
      if (warp == 10) {
        const uint32_t* src = g_mod + 2 * DM + cj * 128 + lane * 4;
        const uint2 wr = *reinterpret_cast<const uint2*>(P.w_r + cj * 128 + lane * 4);
        uint4 vga, vsb, vcb, vgb;
        uint32_t n = 0;
        do {
          vga = ld_relaxed4(src); vsb = ld_relaxed4(src + DM); vcb = ld_relaxed4(src + 2 * DM); vgb = ld_relaxed4(src + 3 * DM);
          watchdog(n);
        } while (!__all_sync(0xffffffffu, tag_ok(vga, tag) && tag_ok(vsb, tag) && tag_ok(vcb, tag) && tag_ok(vgb, tag)));
        const float c0 = rbf(1.f + bf_hi(vcb.x)), c1 = rbf(1.f + bf_hi(vcb.y)), c2 = rbf(1.f + bf_hi(vcb.z)), c3 = rbf(1.f + bf_hi(vcb.w));
        const float a0 = c0 * bf_lo(wr.x), a1 = c1 * bf_hi(wr.x), a2 = c2 * bf_lo(wr.y), a3 = c3 * bf_hi(wr.y);
        const uint32_t h0 = pack_bf(a0, a1), h1 = pack_bf(a2, a3);
        const uint32_t t1 = par + PAR_T1 + (lane >> 2) * 64 + (lane & 1) * 32 + (lane & 2) * 2;
        sts1(t1, h0); sts1(t1 + 8, pack_bf(a0 - bf_lo(h0), a1 - bf_hi(h0)));
        sts1(t1 + 16, h1); sts1(t1 + 24, pack_bf(a2 - bf_lo(h1), a3 - bf_hi(h1)));
        const uint32_t tg = par + PAR_SINK + (lane >> 3) * 64 + (lane & 1) * 32 + (lane & 6) * 2;
        sts1(tg, __byte_perm(vga.x, vga.y, 0x7632)); sts1(tg + 16, __byte_perm(vga.z, vga.w, 0x7632));
        sts4(par + PAR_T2 + lane * 32, make_uint4(pack_bf(c0, c1), __byte_perm(vsb.x, vsb.y, 0x7632), __byte_perm(vgb.x, vgb.y, 0x7632), __byte_perm(vga.x, vga.y, 0x7632)));
        sts4(par + PAR_T2 + lane * 32 + 16, make_uint4(pack_bf(c2, c3), __byte_perm(vsb.z, vsb.w, 0x7632), __byte_perm(vgb.z, vgb.w, 0x7632), __byte_perm(vga.z, vga.w, 0x7632)));
      } else {
        const uint4 g = poll4((lane & 2) ? g_mod + 8 - (lane & 1) * 4 : g_mod + 5 * DM + b * 8 + (lane & 1) * 4, tag);
        sts1(par + PAR_CONST + 60, 0);
        if (lane < 2) sts4(par + PAR_CONST + 16 + lane * 16, g);
        else if (lane < 4) sts2(par + PAR_CONST + (lane - 2) * 8, __float_as_uint(untag_sum(g.x, g.y) + untag_sum(g.z, g.w)), epoch);
      }
      __syncwarp();
#pragma unroll 4
      for (int q = 0; q < 32; q++) st_b128(g_xch + ((size_t)b * 8 * 256 + q * 64 + t2) * 4, (epoch & 1) << 16, 0, 0, 0);
      for (int q = 0; q < 2; q++) st_relaxed4(g_stats + ((size_t)cj * SEQ + rb * 128 + q * 64 + t2) * 4, 0, 0, 0, 0);
      if (b < NFFN)
        for (int q = 0; q < 4; q++) st_relaxed4(g_ypart + ((size_t)(q * 32 + (t2 >> 1)) * NFFN + b) * 8 + (t2 & 1) * 4, 0, 0, 0, 0);
      st_relaxed4(g_row + rb * 2 * DM + (t2 >> 5) * DM + cj * 128 + (t2 & 31) * 4, 0, 0, 0, 0);
      __threadfence();
      mbar_arrive(bar_par);
      mbar_wait(bar_gate, 0);
      uint32_t have = 0, n = 0;
      while (true) {
        const uint32_t st = lds1(par + PAR_CONST + 60) >> 7;
        if ((st & 31) != have) {
          const uint32_t* hsrc = g_row + (st & 15) * 2 * DM + t2 * 4;
          uint4 hv[4];
          bool ok = true;
#pragma unroll
          for (int i = 0; i < 4; i++) hv[i] = ld_pairs(hsrc + i * 256);
#pragma unroll
          for (int i = 0; i < 4; i++) {
            sts2(base + ((FT_G >> i * 4) & 15) * UNIT + (warp & 1) * 8192 + 256 + lane * 8, hv[i].x, hv[i].z);
            ok = ok && hv[i].y == tag && hv[i].w == tag;
          }
          have = __all_sync(0xffffffffu, ok) ? st & 31 : 0;
        }
        if ((st ^ have) == 32) break;
        watchdog(n);
      }
      mbar_arrive(bar_sel);
    }
    __syncwarp();
    cluster_arrive();
    {
      const uint32_t tag = epoch % 3 + 1, t3 = tid - 256;
      mbar_wait(bar_win, 0);
      uint2 win = lds2(par + PAR_CONST + 56);
      win.y &= 0x7ff;
      const uint32_t* fsrc = g_row + (win.y >> 7) * 2 * DM + (b >> 1) * 16 + (t3 & 3) * 4 + (b & 1) * 2;
      const uint32_t* ysrc = g_ypart + (size_t)b * NFFN * 8 + min(t3, NFFN - 1) * 4;
      uint2 fh = ld_pair(fsrc), fx = ld_pair(fsrc + DM);
      if (PSL) __nanosleep(PSL);
      uint4 ya = ld_relaxed4(ysrc), yb = ld_relaxed4(ysrc + NFFN * 4);
      const float rwin = __uint_as_float(((int)win.x < 0 ? win.x & 0x7fffffffu : ~win.x) & ~0x1ffu);
      const float rs = rbf(rcp(1.f + __expf(-rbf(rwin))));
      uint32_t n = 0;
      while (__any_sync(0xffffffffu, fh.y != tag || fx.y != tag)) { fh = ld_pair(fsrc); fx = ld_pair(fsrc + DM); watchdog(n); }
      while (!__all_sync(0xffffffffu, tag_ok(ya, tag) && tag_ok(yb, tag))) {
        if (!tag_ok(ya, tag)) ya = ld_relaxed4(ysrc);
        if (!tag_ok(yb, tag)) yb = ld_relaxed4(ysrc + NFFN * 4);
        watchdog(n);
      }
      __syncwarp();
      PROF(8, t3 == 0, 5);
      float y0 = untag_sum(ya.x, yb.x), y1 = untag_sum(ya.y, yb.y), y2 = untag_sum(ya.z, yb.z), y3 = untag_sum(ya.w, yb.w);
      const bool u1 = lane & 2, u2 = lane & 4;
      y0 = (u1 ? y2 : y0) + __shfl_xor_sync(0xffffffffu, u1 ? y0 : y2, 2);
      y1 = (u1 ? y3 : y1) + __shfl_xor_sync(0xffffffffu, u1 ? y1 : y3, 2);
      y0 = (u2 ? y1 : y0) + __shfl_xor_sync(0xffffffffu, u2 ? y0 : y1, 4);
      y0 += __shfl_xor_sync(0xffffffffu, y0, 8);
      if (!(lane & 8)) sts1(par + PAR_RED + 64 + (t3 >> 4) * 32 + ((lane & 1) * 4 + (lane & 2) + ((lane >> 2) & 1)) * 4, __float_as_uint(y0));
      bar_sync(4, 128);
      if (t3 < 4) {
        y0 = 0.f; y1 = 0.f;
#pragma unroll
        for (int w4 = 0; w4 < 7; w4++) {
          const uint2 v = lds2(par + PAR_RED + 64 + w4 * 32 + t3 * 8);
          y0 += __uint_as_float(v.x); y1 += __uint_as_float(v.y);
        }
        const uint2 gv = lds2(par + PAR_CONST + 16 + t3 * 8);
        const uint32_t upd = hmul2(pack_bf(y0, y1), pack_bf(rs, rs));
        *reinterpret_cast<uint32_t*>(P.out + (size_t)win.y * DM + b * 8 + t3 * 2) =
            hadd2(fx.x, hmul2(__byte_perm(gv.x, gv.y, 0x7632), hadd2(fh.x, upd)));
        if (b == 0 && t3 == 0) st_relaxed(&g_epoch, epoch + 1);
      }
      PROF(31, t3 == 0, 36);
    }
    cluster_wait();
  } else {
    const int wg = warp >> 2;

    uint32_t tag;
    {
      uint32_t* const pmod = g_modp + rank * 2 * DM + (b >> 1) * 32 + lane;
      uint32_t* const pln = g_ln1 + (rb * 128 + cj * 16 + warp) * 4;
      const uint32_t cv = ldg_nc1(P.c + rank * 512 + tid * 2);
      const uint32_t epoch = ld_relaxed(&g_epoch);
      if (warp == 0) st_relaxed(pmod, 0);
      if (lane == 0) { st_b128(pln, 0, 0, 0, 0); st_b128(pln + 32, 0, 0, 0, 0); }
      asm volatile("setmaxnreg.inc.sync.aligned.u32 232;");
      sts1(par + tid * 4, pack_bf(silu_f(bf_lo(cv)), silu_f(bf_hi(cv))));
      bar_sync(1, 320);
      tag = epoch % 3 + 1;
#pragma unroll
      for (int part = 0; part < 3; part++) {
        if (part != 1) {
          const uint32_t xa = base + (2 + part / 2) * GST_BYTES + warp * 2048 + lane * 16;
          mbar_wait(bar_hx + part * 4, 0);
          float s0 = 0.f, s1 = 0.f, q0 = 0.f, q1 = 0.f;
#pragma unroll
          for (int q = 0; q < 4; q++) {
            const uint4 xv = lds4(xa + q * 512);
            const uint32_t u[4] = {xv.x, xv.y, xv.z, xv.w};
#pragma unroll
            for (int e = 0; e < 4; e++) { const float lo = bf_lo(u[e]), hi = bf_hi(u[e]); s0 += lo; s1 += hi; q0 += lo * lo; q1 += hi * hi; }
          }
          s0 += s1; q0 += q1;
#pragma unroll
          for (int o = 16; o > 0; o >>= 1) { s0 += __shfl_xor_sync(0xffffffffu, s0, o); q0 += __shfl_xor_sync(0xffffffffu, q0, o); }
          const float mean = s0 * (1.f / DM);
          float mb, sd;
          ln_scalars(mean, fmaxf(q0 * (1.f / DM) - mean * mean, 0.f), mb, sd);
          uint32_t ih, il;
          split_inv(sd, ih, il);
          if (lane == 0) st_b128(pln + part * 16, pack_bf(mb, mb), ih, il, tag);
          PROF(1, tid == 0 && part == 2, 4);
        } else {
          const uint32_t fr = (lane & 7) + (lane >> 4) * 8, tq = lane & 3;
          const uint32_t wa = stage + warp * 4096 + fr * 64 + ((((lane >> 3) & 1) ^ ((fr >> 1) & 3)) << 4);
          uint32_t sc[8];
#pragma unroll
          for (int k = 0; k < 8; k++) sc[k] = lds1(par + warp * 128 + k * 16 + tq * 4);
          float d0[4] = {0.f, 0.f, 0.f, 0.f}, d1[4] = {0.f, 0.f, 0.f, 0.f};
          mbar_wait(bar_hw, 0);
#pragma unroll
          for (int ks = 0; ks < 4; ks++) {
            uint32_t w[8];
            ldmatrix4t(wa + ks * 1024, w[0], w[1], w[2], w[3]);
            ldmatrix4t((wa ^ 32) + ks * 1024, w[4], w[5], w[6], w[7]);
            mma16816(d0, w[0], w[1], w[2], w[3], sc[2 * ks], sc[2 * ks + 1]);
            mma16816(d1, w[4], w[5], w[6], w[7], sc[2 * ks], sc[2 * ks + 1]);
          }
          sts1(base + 2 * GST_BYTES + warp * 2048 + (tq * 8 + (lane >> 2)) * 4, __float_as_uint((tq & 2) ? ((tq & 1) ? d1[2] : d1[0]) : ((tq & 1) ? d0[2] : d0[0])));
          bar_sync(1, 256);
          if (warp == 0) {
            float s = 0.f;
#pragma unroll
            for (int w8 = 0; w8 < 8; w8++) s += __uint_as_float(lds1(base + 2 * GST_BYTES + w8 * 2048 + lane * 4));
            st_relaxed(pmod, (__float_as_uint(s) & ~3u) | tag);
          }
          PROF(1, tid == 0, 3);
        }
      }
      cluster_wait();
      if (wg == 1) bar_arrive(2, 256);
    }

    float f0 = 0.f, f1 = 0.f;
    const uint32_t rempty = lane < 2 ? mapa(bempty, lane & 1) : 0;
    constexpr uint32_t GE = NSLOT * 8 + 32;
    float o[64], s[64];
#pragma unroll 1
    for (int ps = 0; ps < 3; ps++) {
      {
        const uint32_t xt = ps == 1 ? XT1 : XT2, wt = ps == 1 ? WT1 : WT2;
        const int nst = ps == 2 ? 28 : 14;
        if (ps == 0) {
          float ga[64], gb[64];
#pragma unroll
          for (int i = 0; i < 64; i++) { ga[i] = 0.f; gb[i] = 0.f; }
          uint32_t a[2][16];
          const uint32_t l = fresh_lane();
          uint32_t fa[4];
#pragma unroll
          for (int kk = 0; kk < 4; kk++) fa[kk] = (base + wg * 8192 + frag_offset(warp)) ^ (kk * 32);
          const uint32_t mt = par + (l & 3) * 16;
          auto fetch = [&](int i, uint32_t (&f)[16], uint32_t z) {
            mbar_wait(xfull + (i & 3) * 8, i >> 2);
#pragma unroll
            for (int kk = 0; kk < 4; kk++) ldmatrix4(fa[kk] + (i & 3) * GST_BYTES + z, f[4 * kk], f[4 * kk + 1], f[4 * kk + 2], f[4 * kk + 3]);
          };
          uint4 r0, r1;
          {
            const uint32_t t7 = (warp & 3) * 32 + l;
            const uint32_t* pm = g_modp + wg * DM + ((cj * 128 + t7 * 4) & (DM - 1));
            const uint32_t* pr = g_ln1 + (rb * 128 + warp * 16 + (l >> 2)) * 4;
            uint4 m0 = ld_relaxed4(pm), m1 = ld_relaxed4(pm + 2 * DM);
            r0 = ld_b128(pr); r1 = ld_b128(pr + 32);
            fetch(0, a[0], 0); fetch(1, a[1], 0);
            uint32_t n = 0;
            bool written = false;
#pragma unroll 1
            while (true) {
              uint32_t miss;
              asm volatile("{ .reg .pred p0, p1, p2, p3; .reg .b32 t, u;\n"
                           "lop3.b32 t, %1, %2, %19, 0x7e; lop3.b32 u, %3, %4, %19, 0x7e; or.b32 t, t, u; and.b32 t, t, 3; setp.ne.u32 p0, t, 0;\n"
                           "lop3.b32 t, %5, %6, %19, 0x7e; lop3.b32 u, %7, %8, %19, 0x7e; or.b32 t, t, u; and.b32 t, t, 3; setp.ne.u32 p1, t, 0;\n"
                           "setp.ne.u32 p2, %12, %19; setp.ne.u32 p3, %16, %19;\n"
                           "@p0 ld.relaxed.gpu.global.v4.u32 {%1, %2, %3, %4}, [%17];\n"
                           "@p1 ld.relaxed.gpu.global.v4.u32 {%5, %6, %7, %8}, [%17 + 8192];\n"
                           "@p2 ld.relaxed.gpu.global.v4.u32 {%9, %10, %11, %12}, [%18];\n"
                           "@p3 ld.relaxed.gpu.global.v4.u32 {%13, %14, %15, %16}, [%18 + 128];\n"
                           "or.pred p0, p0, p1; or.pred p2, p2, p3; vote.sync.any.pred p0, p0, 0xffffffff; vote.sync.any.pred p2, p2, 0xffffffff;\n"
                           "selp.u32 t, 1, 0, p0; selp.u32 u, 2, 0, p2; or.b32 %0, t, u; }"
                           : "=r"(miss), "+r"(m0.x), "+r"(m0.y), "+r"(m0.z), "+r"(m0.w), "+r"(m1.x), "+r"(m1.y), "+r"(m1.z), "+r"(m1.w),
                             "+r"(r0.x), "+r"(r0.y), "+r"(r0.z), "+r"(r0.w), "+r"(r1.x), "+r"(r1.y), "+r"(r1.z), "+r"(r1.w)
                           : "l"(pm), "l"(pr), "r"(tag) : "memory");
              if (!(miss & 1) && !written) {
                written = true;
                float c0 = untag_sum(m0.x, m1.x), c1 = untag_sum(m0.y, m1.y), c2 = untag_sum(m0.z, m1.z), c3 = untag_sum(m0.w, m1.w);
                if (wg) { c0 = 1.f + rbf(c0); c1 = 1.f + rbf(c1); c2 = 1.f + rbf(c2); c3 = 1.f + rbf(c3); }
                const uint32_t d = par + (t7 >> 2) * 64 + (t7 & 1) * 32 + (t7 & 2) * 2 + (wg ? 0 : 8);
                sts1(d, pack_bf(c0, c1));
                sts1(d + 16, pack_bf(c2, c3));
                mbar_arrive(bar_mod);
              }
              if (!miss) break;
              watchdog(n);
            }
          }
          const uint32_t zero = r0.w ^ tag;
          auto normalize = [&](uint32_t (&f)[16]) {
#pragma unroll
            for (int k = 0; k < 16; k += 2) { f[k] = ln_norm(f[k], r0.x, r0.y, r0.z); f[k + 1] = ln_norm(f[k + 1], r1.x, r1.y, r1.z); }
          };
          auto modulate = [&](int i, uint32_t (&f)[16]) {
#pragma unroll
            for (int kk = 0; kk < 4; kk++) {
              const uint4 m = lds4(mt + i * 256 + kk * 64);
              f[4 * kk] = MODUL(f[4 * kk], m.x, m.z); f[4 * kk + 1] = MODUL(f[4 * kk + 1], m.x, m.z);
              f[4 * kk + 2] = MODUL(f[4 * kk + 2], m.y, m.w); f[4 * kk + 3] = MODUL(f[4 * kk + 3], m.y, m.w);
            }
            keep(f);
            mbar_arrive_pred(xempty + (i & 3) * 8, l == 0);
          };
          auto publish = [&](int u, uint32_t (&f)[16]) {
#pragma unroll
            for (int kk = 0; kk < 4; kk++) stmatrix4(fa[kk] + OFF_STAGE + u * UNIT, f[4 * kk], f[4 * kk + 1], f[4 * kk + 2], f[4 * kk + 3]);
            __syncwarp();
            mbar_arrive_pred(bar_hpub + u * 8, l == 0);
          };
          auto multiply = [&](int i, uint32_t (&f)[16]) {
            mbar_wait(gfull + (i & 3) * 8, i >> 2);
            const uint64_t db = make_desc(base + (i & 3) * GST_BYTES + UNIT, 8192, 1024);
            wg_fence();
#pragma unroll
            for (int kk = 0; kk < 4; kk++) mma256_rs(ga, gb, f[4 * kk], f[4 * kk + 1], f[4 * kk + 2], f[4 * kk + 3], db + kk * 128);
            wg_commit();
          };
          auto next = [&](int i, uint32_t (&f)[16]) {
            wg_wait<1>();
            mbar_arrive_cl(rempty, GE + ((i + 2) & 3) * 8);
            uint32_t z = zero;
#pragma unroll
            for (int k = 0; k < 16; k += 2) asm volatile("lop3.b32 %0, %1, %2, %0, 0xA8;" : "+r"(z) : "r"(f[k]), "r"(f[k + 1]));
            fetch(i, f, z);
            normalize(f); modulate(i, f); multiply(i, f);
          };
          normalize(a[0]); normalize(a[1]);
          keep(a[0]); keep(a[1]);
          mbar_wait(bar_mod, 0);
          PROF(1, tid == 0, 2);
          modulate(0, a[0]); multiply(0, a[0]); publish(0, a[0]);
          modulate(1, a[1]); multiply(1, a[1]); publish(1, a[1]);
#pragma unroll 1
          for (int i = 2; i < NRS; i += 2) { next(i, a[0]); next(i + 1, a[1]); }
          wg_wait<1>();
          mbar_arrive_cl(rempty, GE + ((NRS + 2) & 3) * 8);
#pragma unroll 1
          for (int i = NRS; i < 14; i++) {
            mbar_wait(xfull + (i & 3) * 8, (i >> 2) & 1);
            mbar_wait(gfull + (i & 3) * 8, (i >> 2) & 1);
            const uint32_t xa = base + (i & 3) * GST_BYTES;
            const uint64_t da = make_desc(xa + wg * 8192, 16, 1024), db = make_desc(xa + UNIT, 8192, 1024);
            if (i == 13) bar_sync(2 + wg, 256);
            wg_fence();
#pragma unroll
            for (int kk = 0; kk < 4; kk++) mma256_ss(ga, gb, da + kk * 2, db + kk * 128, 1);
            wg_commit();
            if (i == 13) bar_arrive(3 - wg, 256);
            wg_wait<1>();
            uint32_t z = zero;
#pragma unroll
            for (int k = 0; k < 16; k += 2) asm volatile("lop3.b32 %0, %1, %2, %0, 0xA8;" : "+r"(z) : "r"(a[1][k]), "r"(a[1][k + 1]));
            mbar_arrive_cl(rempty, GE + ((i + 3) & 3) * 8 + z);
            mbar_arrive_pred(xempty + ((i + 3) & 3) * 8, l == 0 && i != NRS);
          }
          mbar_wait(xfull + 16, 1);
          wg_wait<0>();
          keep(ga); keep(gb);
#pragma unroll
          for (int i = 0; i < 64; i++) {
            asm volatile("mov.b32 %0, %1;" : "=f"(s[i]) : "f"(ga[i]));
            asm volatile("mov.b32 %0, %1;" : "=f"(o[i]) : "f"(gb[i]));
          }
        } else {
          float ga[64], gb[64];
#pragma unroll
          for (int i = 0; i < 64; i++) {
            asm volatile("mov.b32 %0, %1;" : "=f"(ga[i]) : "f"(s[i]));
            asm volatile("mov.b32 %0, %1;" : "=f"(gb[i]) : "f"(o[i]));
          }
#pragma unroll 1
          for (int i = 0; i < nst; i++) {
            mbar_wait(gfull + (i & 3) * 8, (i >> 2) & 1);
            const uint64_t da = make_desc(base + unit_of(xt, i & 3) + wg * 8192, 16, 1024), db = make_desc(base + unit_of(wt, i & 3), 8192, 1024);
            if (i == nst - 1) bar_sync(2 + wg, 256);
            wg_fence();
#pragma unroll
            for (int kk = 0; kk < 4; kk++) mma256_ss(ga, gb, da + kk * 2, db + kk * 128, kk ? 1 : i);
            wg_commit();
            if (i == nst - 1) bar_arrive(3 - wg, 256);
            wg_wait<1>();
            mbar_arrive_cl(rempty, GE + ((i + 3) & 3) * 8, i != 0);
            PROF(4, tid == 0 && (i & 3) == 0, 40 + (ps - 1) * 4 + i / 4);
          }
          wg_wait<0>();
          keep(ga); keep(gb);
#pragma unroll
          for (int i = 0; i < 64; i++) {
            asm volatile("mov.b32 %0, %1;" : "=f"(s[i]) : "f"(ga[i]));
            asm volatile("mov.b32 %0, %1;" : "=f"(o[i]) : "f"(gb[i]));
          }
        }
        mbar_arrive_cl(rempty, GE + (ps == 2 ? 24 : 8));
        if (ps == 2) break;
      }
      const uint32_t qw = base + wg * 8192, qt = QT >> (16 * ps), at = ps ? AT1 : AT0;
      {
        const uint32_t wt = ps ? WT1 : WT0;
        const uint64_t da0 = make_desc(qw + unit_of(qt, 2), 16, 1024), da1 = make_desc(qw + unit_of(qt, 3), 16, 1024);
        const uint64_t db0 = make_desc(base + unit_of(wt, 2), 8192, 1024), db1 = make_desc(base + unit_of(wt, 3), 8192, 1024);
        mbar_wait(gfull + 16, 1);
        bar_sync(2 + wg, 256);
        wg_fence();
#pragma unroll
        for (int kk = 0; kk < 4; kk++) mma_ss<1>(s, da0 + kk * 2, db0 + kk * 128, 1);
        wg_commit();
        mbar_wait(xfull + 24, 1);
        mbar_wait(gfull + 24, 1);
        wg_fence();
#pragma unroll
        for (int kk = 0; kk < 4; kk++) mma_ss<1>(s, da1 + kk * 2, db1 + kk * 128, 1);
        wg_commit();
        bar_arrive(3 - wg, 256);
        mbar_wait(ps == 0 ? bar_pread : bar_ofree + 8, 0);
        wg_wait<0>();
        keep(s);
        PROF(2, tid == 0, 8 + ps * 8);
        store_chunk<0>(s, qw + unit_of(qt, 0) + frag_offset(warp));
        store_chunk<1>(s, qw + unit_of(qt, 1) + frag_offset(warp));
        fence_async_smem();
        bar_sync(2 + wg, 256);
        wg_fence();
#pragma unroll
        for (int kk = 0; kk < 8; kk++) mma_ss<1>(o, (kk < 4 ? da0 : da1) + (kk & 3) * 2, (kk < 4 ? db0 : db1) + UNIT / 16 + (kk & 3) * 128, 1);
        wg_commit();
        mbar_wait(bfull, 0);
        wg_fence();
        issue_qk(s, qw + unit_of(qt, 0), qw + unit_of(qt, 1), base + unit_of(at, 0));
        wg_commit();
        bar_arrive(3 - wg, 256);
        wg_wait<1>();
        keep(o);
        mbar_arrive_cl(rempty, GE + 16);
        mbar_arrive_cl(rempty, GE + 24);
        store_chunk<0>(o, qw + unit_of(qt, 2) + frag_offset(warp));
        store_chunk<1>(o, qw + unit_of(qt, 3) + frag_offset(warp));
        wg_wait<0>();
        keep(s);
        mbar_arrive_cl(rempty, 0);
      }
      PROF(4, tid == 0 && ps == 1, 61);
      float l0 = 0.f, l1 = 0.f;
      auto step = [&](auto odd_c, const int j, uint32_t (&pw)[32], uint32_t (&pr)[32]) {
        constexpr bool ODD = decltype(odd_c)::value;
        const bool first = !ODD && (j & 2) == 0, last = ODD && j == 7;
        const uint32_t ph = (j >> 1) & 1;
        float i0, i1, a0, a1;
        const bool so = !ODD && j == 4;
        if (so) { i0 = inv_quad_sum(l0); i1 = inv_quad_sum(l1); l0 = 0.f; l1 = 0.f; }
        bool redo = !ODD && (j | ps) == 0;
        while (true) {
          if (redo) {
            float m0 = fmaxf(s[0], s[1]), m1 = fmaxf(s[2], s[3]);
#pragma unroll
            for (int i = 1; i < 16; i++) { m0 = fmaxf(m0, fmaxf(s[4 * i], s[4 * i + 1])); m1 = fmaxf(m1, fmaxf(s[4 * i + 2], s[4 * i + 3])); }
            m0 = fmaxf(m0, __shfl_xor_sync(0xffffffffu, m0, 1)); m1 = fmaxf(m1, __shfl_xor_sync(0xffffffffu, m1, 1));
            m0 = fmaxf(m0, __shfl_xor_sync(0xffffffffu, m0, 2)); m1 = fmaxf(m1, __shfl_xor_sync(0xffffffffu, m1, 2));
            m0 *= SCL2; m1 *= SCL2;
            if (!first) {
              m0 = fmaxf(m0, f0); m1 = fmaxf(m1, f1);
              const float c0 = ex2(f0 - m0), c1 = ex2(f1 - m1);
              l0 *= c0; l1 *= c1;
              wg_wait<0>();
              keep(o);
#pragma unroll
              for (int i = 0; i < 16; i++) { o[4 * i] *= c0; o[4 * i + 1] *= c0; o[4 * i + 2] *= c1; o[4 * i + 3] *= c1; }
            }
            f0 = m0; f1 = m1;
          }
          float b0 = 0.f, b1 = 0.f;
          a0 = 0.f; a1 = 0.f;
#pragma unroll
          for (int i = 0; i < 16; i++) {
            const float e0 = ex2(fmaf(s[4 * i], SCL2, -f0)), e1 = ex2(fmaf(s[4 * i + 1], SCL2, -f0));
            const float e2 = ex2(fmaf(s[4 * i + 2], SCL2, -f1)), e3 = ex2(fmaf(s[4 * i + 3], SCL2, -f1));
            a0 += e0; b0 += e1; a1 += e2; b1 += e3;
            pw[2 * i] = pack_bf(e0, e1); pw[2 * i + 1] = pack_bf(e2, e3);
            if (i == VREL) {
#pragma unroll
              for (int k = 0; k < 2 * VREL + 2; k++) asm volatile("" : "+r"(pw[k])::"memory");
              mbar_wait(bar_mod, 0);
              wg_wait<0>();
              mbar_arrive_cl(rempty, ODD ? 16 : 0, !redo && (ODD || j));
#pragma unroll
              for (int k = 4 * VREL + 4; k < 64; k++) asm volatile("" : "+f"(s[k])::"memory");
            }
          }
          a0 += b0; a1 += b1;
          if (redo) break;
          redo = __any_sync(0xffffffffu, !(a0 + a1 < 0x1p90f));
          if (first) {
            uint32_t m0 = __ballot_sync(0xffffffffu, a0 > 0x1p-80f), m1 = __ballot_sync(0xffffffffu, a1 > 0x1p-80f);
            m0 |= m0 >> 1; m1 |= m1 >> 1; m0 |= m0 >> 2; m1 |= m1 >> 2;
            redo = redo || (m0 & m1 & 0x11111111u) != 0x11111111u;
          }
          if (!redo) break;
        }
        l0 += a0; l1 += a1;
        keep(pw);
        keep(o);
        if (so) store_chunk<0>(o, i0, i1, qw + unit_of(qt, 0) + frag_offset(warp));
        keep(o);
        if (ODD && !(j & 2)) { fence_async_smem(); mbar_arrive_pred(bar_ofull + wg * 8, j > 4); }
        mbar_wait(bfull + (ODD ? 24 : 8), ph);
        bar_sync(2 + wg, 256);
        if (!last) {
          const uint32_t qn = qt >> (j >= 3 ? 8 : 0);
          wg_fence();
          issue_qk(s, qw + unit_of(qn, 0), qw + unit_of(qn, 1), base + unit_of(at, ODD ? 3 : 1));
          wg_commit();
          mbar_wait(bfull + (ODD ? 0 : 16), ODD ? ph ^ 1 : ph);
        }
        if (so) { store_chunk<1>(o, i0, i1, qw + unit_of(qt, 1) + frag_offset(warp)); keep(o); }
        wg_fence();
        issue_pv(o, pw, base + unit_of(at, ODD ? (last ? 3 : 0) : 2), !first);
        wg_commit();
        bar_arrive(3 - wg, 256);
        wg_wait<1>();
        keep(s);
        mbar_arrive_cl(rempty, ODD ? 24 : 8, !last);
        PROF(4, tid == 0 && ps == 1, 51 + j);
      };
      uint32_t pa[32], pb[32];
#pragma unroll 1
      for (int j = 0; j < 8; j += 2) {
        step(std::false_type{}, j, pa, pb);
        step(std::true_type{}, j + 1, pb, pa);
      }
      {
        const float i0 = inv_quad_sum(l0), i1 = inv_quad_sum(l1);
        wg_wait<0>();
        keep(o);
        mbar_arrive_cl(rempty, 24);
        store_chunk<0>(o, i0, i1, qw + unit_of(qt, 2) + frag_offset(warp));
        store_chunk<1>(o, i0, i1, qw + unit_of(qt, 3) + frag_offset(warp));
        fence_async_smem();
        mbar_arrive(bar_ofull + 16 + wg * 8);
      }
      PROF(2, tid == 0, 10 + ps * 8);
    }

    const int ln = fresh_lane(), g = ln >> 2, tq = ln & 3, ct = warp * 32 + ln;
    const bool lane0 = ln == 0;
    const int lrow0 = warp * 16 + g;
    const int grow0 = rb * 128 + lrow0;
    const uint32_t res = base + OFF_RES, trow = res + wg * 8192 + frag_offset(warp);
    uint32_t xr[32];
    uint4 sv[4], own;
    uint32_t* sp[4];
#pragma unroll
    for (int k = 0; k < 4; k++) sp[k] = g_stats + ((((tq >> 1) * 4 + k) ^ cj) * SEQ + grow0 + (tq & 1) * 8) * 4;
    {
      const uint64_t da = make_desc(base + wg * 8192, 16, 1024), db = make_desc(base, 8192, 1024);
      constexpr int U = UNIT / 16;
#define HALF_STAGE(acc, xu, wu) _Pragma("unroll") for (int kk = 0; kk < 4; kk++) mma_ss<1>(acc, da + (xu) * U + kk * 2, db + (wu) * U + kk * 128, 1)
      PROF(10, ct == PT, 19); STAMP(0);
      cluster_arrive();
      mbar_wait(gfull, 1);
      mbar_wait(gfull + 8, 1);
      bar_sync(2 + wg, 256);
      wg_fence();
      HALF_STAGE(o, 7, 1);
      HALF_STAGE(o, 8, 3);
      wg_commit();
      STAMP(16);
      mbar_wait(gfull + 16, 1);
      STAMP(17);
      wg_fence();
      HALF_STAGE(o, 6, 11);
      wg_commit();
      bar_arrive(3 - wg, 256);
      mbar_wait(bar_par, 0);
      uint32_t* xo = g_xch + ((size_t)b * 8 * 256 + ct) * 4;
      const uint32_t* xi = g_xch + ((size_t)(b ^ 2) * 8 * 256 + ct) * 4;
      const uint32_t par1 = (~lds1(par + PAR_CONST + 4) & 1) << 16;
      uint32_t ga[16];
      uint4 bw[8];
#define LOAD_PAR _Pragma("unroll") for (int i = 0; i < 8; i++) {                                                               \
        if (!(i & 1)) {                                                                                                         \
          const uint4 t = lds4(par + PAR_SINK + i * 32 + tq * 16);                                                              \
          ga[2 * i] = t.x; ga[2 * i + 1] = t.y; ga[2 * i + 2] = t.z; ga[2 * i + 3] = t.w;                                       \
        }                                                                                                                       \
        bw[i] = lds4(par + PAR_T1 + i * 64 + tq * 16);                                                                          \
        if (!(g & 1)) { bw[i].x = 0x3f803f80u; bw[i].y = 0x3f803f80u; }                                                         \
      }
      if (PPOS == 0) LOAD_PAR
      wg_wait<1>();
      mbar_arrive_pred(bar_rel, lane0);
      wg_wait<0>();
      keep(o);
      mbar_arrive_pred(bar_ring, lane0);
      PROF(8, ct == PT, 20); STAMP(1);
#define SEND(i) st_b128(xo + (i) * 1024, (pack_bf(o[8 * (i)], o[8 * (i) + 1]) & ~0x10000u) | par1, pack_bf(o[8 * (i) + 2], o[8 * (i) + 3]), \
                        pack_bf(o[8 * (i) + 4], o[8 * (i) + 5]), pack_bf(o[8 * (i) + 6], o[8 * (i) + 7]))
#pragma unroll
      for (int i = 0; i < NS1; i++) SEND(i);
      PROF(8, ct == PT, 21); STAMP(2);
      bar_sync(2 + wg, 256);
      wg_fence();
      HALF_STAGE(s, 7, 0);
      HALF_STAGE(s, 8, 2);
      HALF_STAGE(s, 6, 10);
      wg_commit();
      bar_arrive(3 - wg, 256);
      STAMP(18);
      mbar_wait(gfull + 24, 1);
#pragma unroll
      for (int i = NS1; i < 8; i++) SEND(i);
      uint4 v[8];
#pragma unroll
      for (int i = 0; i < 4; i++) v[i] = ld_b128(xi + i * 1024);
      if (PPOS == 1) LOAD_PAR
      STAMP(19);
      mbar_wait(bar_xres, 0);
      wg_wait<0>();
      mbar_arrive_pred(bar_ring + 8, lane0);
      bar_sync(2 + wg, 256);
      STAMP(20);
#pragma unroll
      for (int i = 4; i < 8; i++) v[i] = ld_b128(xi + i * 1024);
      mbar_wait(bar_xres, 0);
      wg_fence();
      HALF_STAGE(s, 9, 4);
      wg_commit();
      mbar_wait(bar_rx, 0);
      wg_fence();
      HALF_STAGE(s, 1, 5);
      wg_commit();
      bar_arrive(3 - wg, 256);
      STAMP(21);
      wg_wait<0>();
      keep(s);
      mbar_arrive_pred(bar_ring + 16, lane0);
      PROF(10, ct == PT, 23); STAMP(4);
#pragma unroll
      for (int i = 0; i < 16; i += 2) ldmatrix4((trow ^ ((i & 7) << 4)) + (i >> 3) * 16384, xr[2 * i], xr[2 * i + 1], xr[2 * i + 2], xr[2 * i + 3]);
      if (PPOS == 2) LOAD_PAR
      uint32_t pk[32];
      pack_p(s, pk);
      keep(pk);
      {
        uint32_t n = 0, miss;
        do {
          miss = 0;
#pragma unroll
          for (int i = 0; i < 8; i++) miss |= v[i].x ^ par1;
          miss = __any_sync(0xffffffffu, miss & 0x10000u);
          if (miss) {
#pragma unroll
            for (int i = 0; i < 8; i++)
              asm volatile("{ .reg .pred p; .reg .b32 t; xor.b32 t, %0, %5; and.b32 t, t, 0x10000; setp.ne.u32 p, t, 0;\n"
                           "@p ld.relaxed.gpu.global.v4.u32 {%0, %1, %2, %3}, [%4]; }"
                           : "+r"(v[i].x), "+r"(v[i].y), "+r"(v[i].z), "+r"(v[i].w) : "l"(xi + i * 1024), "r"(par1) : "memory");
          }
          watchdog(n);
        } while (miss);
      }
      PROF(8, ct == PT, 22); STAMP(3);
#pragma unroll
      for (int k = 0; k < 4; k++) sv[k] = ESV ? ld_b128(sp[k]) : make_uint4(0, 0, 0, 0);
      float ds[4] = {0.f, 0.f, 0.f, 0.f}, dl[4] = {0.f, 0.f, 0.f, 0.f}, q0[4] = {0.f, 0.f, 0.f, 0.f}, q1[4] = {0.f, 0.f, 0.f, 0.f};
#pragma unroll
      for (int i = 0; i < 8; i++) {
        const uint32_t u0 = hfma2(ga[2 * i], hadd2(pk[4 * i], v[i].x & ~0x10000u), xr[4 * i]);
        const uint32_t u1 = hfma2(ga[2 * i], hadd2(pk[4 * i + 1], v[i].y), xr[4 * i + 1]);
        const uint32_t u2 = hfma2(ga[2 * i + 1], hadd2(pk[4 * i + 2], v[i].z), xr[4 * i + 2]);
        const uint32_t u3 = hfma2(ga[2 * i + 1], hadd2(pk[4 * i + 3], v[i].w), xr[4 * i + 3]);
        xr[4 * i] = u0; xr[4 * i + 1] = u1; xr[4 * i + 2] = u2; xr[4 * i + 3] = u3;
        mma16816(ds, u0, u1, u2, u3, bw[i].x, bw[i].y);
        mma16816(dl, u0, u1, u2, u3, bw[i].z, bw[i].w);
        mma16816(q0, u0, u1, u2, u3, u0, u2);
        mma16816(q1, u0, u1, u2, u3, u1, u3);
      }
      const float sqa = __shfl_sync(0xffffffffu, (g & 1) ? q0[1] : q0[0], g * 4 + (g >> 1));
      const float sqb = __shfl_sync(0xffffffffu, (g & 1) ? q1[3] : q1[2], g * 4 + (g >> 1));
      own = (tq & 1) ? make_uint4(__float_as_uint(ds[2]), __float_as_uint(sqb), __float_as_uint(ds[3] + dl[3]), tag)
                                 : make_uint4(__float_as_uint(ds[0]), __float_as_uint(sqa), __float_as_uint(ds[1] + dl[1]), tag);
      if (tq < 2) st_b128(sp[0], own.x, own.y, own.z, own.w);
    }
    PROF(8, ct == PT, 29); STAMP(5);
    uint32_t mm, ih, il;
    float rbest;
    uint32_t wf[128];
    const uint32_t frow = (ln & 7) + (ln >> 4) * 8;
    const uint32_t wfo = base + (warp & 1) * 8192 + frow * 64 + ((((ln >> 3) & 1) ^ ((frow >> 1) & 3)) << 4);
#define LOAD_WF(m) _Pragma("unroll") for (int f = 0; f < 16; f++) {                                                   \
      const int r = ((f >> 1) * 4 + (m) * 2 + (f & 1)) * 4;                                                           \
      ldmatrix4t(((wfo + unit_of((m) ? FT_U : FT_G, warp >> 1)) ^ ((f & 1) * 32)) + (f >> 1) * 1024, wf[r], wf[r + 1], wf[r + 2], wf[r + 3]); \
    }
    bool early, wait1;
    {
#pragma unroll
      for (int i = 0; i < 16; i += 2) stmatrix4((trow ^ ((i & 7) << 4)) + (i >> 3) * 16384, xr[2 * i], xr[2 * i + 1], xr[2 * i + 2], xr[2 * i + 3]);
      const uint4 cst = lds4(par + PAR_CONST);
      const float A1 = __uint_as_float(cst.x), A2 = __uint_as_float(cst.z);
      uint32_t n = 0;
      early = false; wait1 = false;
#pragma unroll 1
      while (true) {
        uint32_t miss;
        asm volatile("{ .reg .pred p0, p1, p2, p3; .reg .b64 u, v; .reg .b128 w;\n"
                     "setp.ge.u32 p0, %22, 2; setp.ne.and.u32 p0, %4, %21, p0; setp.ne.u32 p1, %8, %21; setp.ne.u32 p2, %12, %21; setp.ne.u32 p3, %16, %21;\n"
                     "@p0 ld.relaxed.gpu.global.v4.u32 {%1, %2, %3, %4}, [%17];\n"
                     "@p1 ld.relaxed.gpu.global.v4.u32 {%5, %6, %7, %8}, [%18];\n"
                     "@p2 ld.relaxed.gpu.global.v4.u32 {%9, %10, %11, %12}, [%19];\n"
                     "@p3 ld.relaxed.gpu.global.v4.u32 {%13, %14, %15, %16}, [%20];\n"
                     "or.pred p0, p0, p1; or.pred p2, p2, p3; or.pred p0, p0, p2; vote.sync.any.pred p0, p0, 0xffffffff; selp.u32 %0, 1, 0, p0; }"
                     : "=r"(miss), "+r"(sv[0].x), "+r"(sv[0].y), "+r"(sv[0].z), "+r"(sv[0].w), "+r"(sv[1].x), "+r"(sv[1].y), "+r"(sv[1].z), "+r"(sv[1].w),
                       "+r"(sv[2].x), "+r"(sv[2].y), "+r"(sv[2].z), "+r"(sv[2].w), "+r"(sv[3].x), "+r"(sv[3].y), "+r"(sv[3].z), "+r"(sv[3].w)
                     : "l"(sp[0]), "l"(sp[1]), "l"(sp[2]), "l"(sp[3]), "r"(tag), "r"(tq) : "memory");
        if (!miss) break;
        wait1 = true;
        if (!early && (b >= NFFN || __all_sync(0xffffffffu, mbar_test(bar_box + (warp >> 1) * 8, 0)))) {
          early = true;
          LOAD_WF(0);
          __syncwarp();
          mbar_arrive_pred(bar_gate, lane0);
        }
        watchdog(n);
      }
      const uint4 v0 = tq < 2 ? own : sv[0], v1 = sv[1], v2 = sv[2], v3 = sv[3];
      PROF(8, ct == PT, 30); STAMP(6);
      float su = (__uint_as_float(v0.x) + __uint_as_float(v1.x)) + (__uint_as_float(v2.x) + __uint_as_float(v3.x));
      float sq = (__uint_as_float(v0.y) + __uint_as_float(v1.y)) + (__uint_as_float(v2.y) + __uint_as_float(v3.y));
      float dt = (__uint_as_float(v0.z) + __uint_as_float(v1.z)) + (__uint_as_float(v2.z) + __uint_as_float(v3.z));
      su += __shfl_xor_sync(0xffffffffu, su, 2); sq += __shfl_xor_sync(0xffffffffu, sq, 2); dt += __shfl_xor_sync(0xffffffffu, dt, 2);
      const float m = su * (1.f / DM);
      float mb, sd;
      ln_scalars(m, fmaxf(sq * (1.f / DM) - m * m, 0.f), mb, sd);
      const float inv = rcp(sd);
      rbest = (dt - mb * A1) * inv + A2;
      mm = pack_bf(mb, mb);
      ih = pack_bf(inv, inv);
      const float lo = inv - bf_lo(ih);
      il = pack_bf(lo, lo);
    }
    int ibest;
    {
      const uint32_t bits = __float_as_uint(rbest);
      const uint32_t key = (((int)bits < 0 ? ~bits : bits | 0x80000000u) & ~0x1ffu) | ((127 - lrow0 - (tq & 1) * 8) << 2) | tag;
      sts1(par + PAR_RED + warp * 4, __reduce_max_sync(0xffffffffu, key));
      PROF(8, ct == PT, 38); STAMP(7);
      uint32_t waited;
      asm volatile("{ .reg .pred p, q; setp.ne.u32 p, %1, 0; barrier.cta.red.or.pred q, 1, 256, p; selp.u32 %0, 1, 0, q; }" : "=r"(waited) : "r"((uint32_t)(wait1 && (wg || CW0))) : "memory");
      const uint4 ka = lds4(par + PAR_RED), kb = lds4(par + PAR_RED + 16);
      const uint32_t k2 = max(max(max(ka.x, ka.y), max(ka.z, ka.w)), max(max(kb.x, kb.y), max(kb.z, kb.w)));
      if (ct == 0 && ((cj & CWM) == 0 || (CWL && !waited))) st_relaxed(g_cand + rb, k2);
      ibest = 127 - ((k2 >> 2) & 127);
    }
    PROF(8, ct == PT, 39); STAMP(8);
    if ((ibest >> 4) == warp) {
      const int src = (ibest & 7) * 4 + ((ibest >> 3) & 1), ch = g * 2;
      const uint32_t cm = __shfl_sync(0xffffffffu, mm, src), ch_ = __shfl_sync(0xffffffffu, ih, src), cl = __shfl_sync(0xffffffffu, il, src);
      const uint32_t xa = res + (ch >> 3) * 16384 + ibest * 128 + (((ch & 7) ^ (ibest & 7)) << 4) + tq * 4;
      const uint32_t x0 = lds1(xa), x1 = lds1(xa ^ 16);
      const uint2 p0 = lds2(par + PAR_T2 + ch * 64 + tq * 16), p1 = lds2(par + PAR_T2 + ch * 64 + 64 + tq * 16);
      uint32_t* dst = g_row + rb * 2 * DM + cj * 128 + ln * 4;
      st_pairs(dst, ln_mod(x0, cm, ch_, cl, p0.x, p0.y), ln_mod(x1, cm, ch_, cl, p1.x, p1.y), tag);
      st_pairs(dst + DM, x0, x1, tag);
      __syncwarp();
    }
    PROF(8, ct == PT, 37); STAMP(9);
    uint32_t wd[64];
    const uint32_t wda = base + unit_of(FT_D, warp >> 1) + (warp & 1) * 8192 + frow * 128 + ((((ln >> 3) & 1) ^ (ln & 7)) << 4);
#define LOAD_WD(f) ldmatrix4t((wda ^ ((((f) >> 1) & 3) * 32)) + ((f) >> 3) * 4096 + ((f) & 1) * 2048, wd[4 * (f)], wd[4 * (f) + 1], wd[4 * (f) + 2], wd[4 * (f) + 3])
    if (!early) {
      if (b < NFFN) mbar_wait(bar_box + (warp >> 1) * 8, 0);
      LOAD_WF(0);
      __syncwarp();
      mbar_arrive_pred(bar_gate, lane0);
    }
    if (b < NFFN) {
      const uint32_t own = base + unit_of(FT_G, warp >> 1) + (warp & 1) * 8192;
      mbar_wait(bar_box + (4 + (warp >> 1)) * 8, 0);
      LOAD_WF(1);
      uint32_t* const ydst = g_ypart + ((size_t)(warp * 16 + tq * 2) * NFFN + b) * 8 + g;
      PROF(8, ct == PT, 31); STAMP(10);
      mbar_wait(bar_box + (8 + (warp >> 1)) * 8, 0);
#pragma unroll
      for (int f = 0; f < WDE; f++) LOAD_WD(f);
      STAMP(11);
      mbar_wait(bar_sel, 0);
      PROF(8, ct == PT, 33); STAMP(12);
      float d[8][4];
#pragma unroll
      for (int i = 0; i < 4; i++) { d[i][0] = 0.f; d[i][1] = 0.f; d[i][2] = 0.f; d[i][3] = 0.f; }
#pragma unroll
      for (int ks = 0; ks < 8; ks++) {
        const uint2 hb = lds2(own + 256 + ks * 32 + tq * 8);
#pragma unroll
        for (int mt = 0; mt < 4; mt++) {
          const int r = ks * 16 + mt * 4;
          mma16816(d[mt], wf[r], wf[r + 1], wf[r + 2], wf[r + 3], hb.x, hb.y);
        }
      }
      sts2(own + (tq * 8 + g) * 8, __float_as_uint((tq & 2) ? ((tq & 1) ? d[1][2] : d[1][0]) : ((tq & 1) ? d[0][2] : d[0][0])),
           __float_as_uint((tq & 2) ? ((tq & 1) ? d[3][2] : d[3][0]) : ((tq & 1) ? d[2][2] : d[2][0])));
      bar_sync(1, 256);
      uint32_t ab[4];
      {
        float G = 0.f, U = 0.f;
        uint2 pv[8];
#pragma unroll
        for (int w8 = 0; w8 < 8; w8++) pv[w8] = lds2(base + ln * 8 + ((FT_G >> (w8 >> 1) * 4) & 15) * UNIT + (w8 & 1) * 8192);
#pragma unroll
        for (int w8 = 0; w8 < 8; w8 += 2) {
          G += __uint_as_float(pv[w8].x) + __uint_as_float(pv[w8 + 1].x);
          U += __uint_as_float(pv[w8].y) + __uint_as_float(pv[w8 + 1].y);
        }
#pragma unroll
        for (int f = WDE; f < 16; f++) LOAD_WD(f);
        const float act = rbf(silu_f(rbf(G))) * rbf(U);
        const uint32_t pk = pack_bf(act, __shfl_down_sync(0xffffffffu, act, 1));
#pragma unroll
        for (int i = 0; i < 4; i++) ab[i] = __shfl_sync(0xffffffffu, pk, i * 8 + tq * 2);
      }
      PROF(8, ct == PT, 34); STAMP(13);
#pragma unroll
      for (int mt = 0; mt < 8; mt++) {
        d[mt][0] = 0.f; d[mt][1] = 0.f; d[mt][2] = 0.f; d[mt][3] = 0.f;
        mma16816(d[mt], wd[mt * 8], wd[mt * 8 + 1], wd[mt * 8 + 2], wd[mt * 8 + 3], ab[0], ab[1]);
        mma16816(d[mt], wd[mt * 8 + 4], wd[mt * 8 + 5], wd[mt * 8 + 6], wd[mt * 8 + 7], ab[2], ab[3]);
      }
#pragma unroll
      for (int i = 0; i < 4; i++) {
        const int m4 = (i >> 1) * 4, e = (i & 1) * 2;
        const float y = (tq & 2) ? ((tq & 1) ? d[m4 + 3][e] : d[m4 + 2][e]) : ((tq & 1) ? d[m4 + 1][e] : d[m4][e]);
        st_relaxed(ydst + (m4 * 2 + (i & 1)) * NFFN * 8, tagf(y, tag));
      }
      PROF(8, ct == PT, 35); STAMP(14);
    }
    mbar_wait(bar_sel, 0);
    mbar_arrive_pred(bar_win, ct == 0);
    const int iwin = lds1(par + PAR_CONST + 60) & 0x7ff;
    const bool cand = (iwin >> 4) == rb * 8 + warp;
    {
      const uint32_t mm0 = __shfl_sync(0xffffffffu, mm, ln & ~1), mm1 = __shfl_sync(0xffffffffu, mm, ln | 1);
      const uint32_t ih0 = __shfl_sync(0xffffffffu, ih, ln & ~1), ih1 = __shfl_sync(0xffffffffu, ih, ln | 1);
      const uint32_t il0 = __shfl_sync(0xffffffffu, il, ln & ~1), il1 = __shfl_sync(0xffffffffu, il, ln | 1);
#pragma unroll 1
      for (int hf = 0; hf < 2; hf++) {
        uint32_t x[16];
#pragma unroll
        for (int i = 0; i < 8; i += 2) ldmatrix4((trow ^ (i << 4)) + hf * 16384, x[2 * i], x[2 * i + 1], x[2 * i + 2], x[2 * i + 3]);
#pragma unroll
        for (int i = 0; i < 8; i++) {
          const uint4 pv = lds4(par + PAR_T2 + (hf * 8 + i) * 64 + tq * 16);
          x[2 * i] = hadd2(x[2 * i], hmul2(pv.z, ln_mod(x[2 * i], mm0, ih0, il0, pv.x, pv.y)));
          x[2 * i + 1] = hadd2(x[2 * i + 1], hmul2(pv.z, ln_mod(x[2 * i + 1], mm1, ih1, il1, pv.x, pv.y)));
        }
#pragma unroll
        for (int i = 0; i < 8; i += 2) stmatrix4((trow ^ (i << 4)) + hf * 16384, x[2 * i], x[2 * i + 1], x[2 * i + 2], x[2 * i + 3]);
      }
      if (!cand) fence_async_smem();
      __syncwarp();
      if (!cand && elect_one()) {
        tma2d_store(&maps.out, res + warp * 2048, cj * 128, rb * 128 + warp * 16);
        tma2d_store(&maps.out, res + 16384 + warp * 2048, cj * 128 + 64, rb * 128 + warp * 16);
        asm volatile("cp.async.bulk.commit_group;" ::: "memory");
      }
    }
    if (cand) {
      const int wrow0 = warp * 16;
#pragma unroll 2
      for (int p = 0; p < 8; p++) {
        const int row = 2 * p + (ln >> 4), ch = ln & 15;
        const uint4 v = lds4(res + (ch >> 3) * 16384 + (wrow0 + row) * 128 + (((ch & 7) ^ (row & 7)) << 4));
        if (rb * 128 + wrow0 + row != iwin) *reinterpret_cast<uint4*>(P.out + (size_t)(rb * 128 + wrow0 + row) * DM + cj * 128 + ch * 8) = v;
      }
    }
    asm volatile("cp.async.bulk.wait_group.read 0;" ::: "memory");
    PROF(8, ct == PT, 11); STAMP(15);
    cluster_wait();
  }
}

typedef CUresult (*EncodeFn)(CUtensorMap*, CUtensorMapDataType, cuuint32_t, void*, const cuuint64_t*, const cuuint64_t*,
                             const cuuint32_t*, const cuuint32_t*, CUtensorMapInterleave, CUtensorMapSwizzle,
                             CUtensorMapL2promotion, CUtensorMapFloatOOBfill);

void map2d(EncodeFn enc, CUtensorMap* m, const void* p, uint64_t rows, uint64_t cols, uint32_t brows) {
  cuuint64_t dims[2] = {cols, rows}, strides[1] = {cols * 2};
  cuuint32_t box[2] = {64, brows}, es[2] = {1, 1};
  enc(m, CU_TENSOR_MAP_DATA_TYPE_BFLOAT16, 2, const_cast<void*>(p), dims, strides, box, es, CU_TENSOR_MAP_INTERLEAVE_NONE,
      CU_TENSOR_MAP_SWIZZLE_128B, CU_TENSOR_MAP_L2_PROMOTION_L2_256B, CU_TENSOR_MAP_FLOAT_OOB_FILL_NONE);
}
void map2d_narrow(EncodeFn enc, CUtensorMap* m, const void* p, uint64_t rows, uint64_t cols, uint32_t brows) {
  cuuint64_t dims[2] = {cols, rows}, strides[1] = {cols * 2};
  cuuint32_t box[2] = {32, brows}, es[2] = {1, 1};
  enc(m, CU_TENSOR_MAP_DATA_TYPE_BFLOAT16, 2, const_cast<void*>(p), dims, strides, box, es, CU_TENSOR_MAP_INTERLEAVE_NONE,
      CU_TENSOR_MAP_SWIZZLE_64B, CU_TENSOR_MAP_L2_PROMOTION_L2_64B, CU_TENSOR_MAP_FLOAT_OOB_FILL_NONE);
}
void map3d(EncodeFn enc, CUtensorMap* m, const void* p, uint64_t rows, uint64_t cols, uint32_t brows, uint32_t nch) {
  cuuint64_t dims[3] = {64, rows, cols / 64}, strides[2] = {cols * 2, 128};
  cuuint32_t box[3] = {64, brows, nch}, es[3] = {1, 1, 1};
  enc(m, CU_TENSOR_MAP_DATA_TYPE_BFLOAT16, 3, const_cast<void*>(p), dims, strides, box, es, CU_TENSOR_MAP_INTERLEAVE_NONE,
      CU_TENSOR_MAP_SWIZZLE_128B, CU_TENSOR_MAP_L2_PROMOTION_L2_256B, CU_TENSOR_MAP_FLOAT_OOB_FILL_NONE);
}

}

extern "C" void kernel_launch(void* const* d_in, const int* in_sizes, int n_in, void* d_out, int out_size) {
  (void)in_sizes; (void)n_in; (void)out_size;
  static EncodeFn enc = nullptr;
  if (!enc) {
    void* fn = nullptr;
    cudaDriverEntryPointQueryResult st;
    cudaGetDriverEntryPoint("cuTensorMapEncodeTiled", &fn, cudaEnableDefault, &st);
    enc = (EncodeFn)fn;
    cudaFuncSetAttribute(fused_kernel, cudaFuncAttributeMaxDynamicSharedMemorySize, SMEM_BYTES);
  }
  Maps maps;
  map2d(enc, &maps.x, d_in[0], SEQ, DM, 128);
  map2d(enc, &maps.out, d_out, SEQ, DM, 16);
  map3d(enc, &maps.wq, d_in[3], DM, NQ, 64, 2);
  map3d(enc, &maps.k, d_in[1], 4 * SK, 128, 128, 1);
  map3d(enc, &maps.v, d_in[2], 4 * SK, 128, 128, 1);
  map3d(enc, &maps.wo, d_in[4], NQ, DM, 64, 2);
  map2d_narrow(enc, &maps.wg, d_in[7], DM, FF, 256);
  map2d_narrow(enc, &maps.wu, d_in[8], DM, FF, 256);
  map3d(enc, &maps.wd, d_in[9], FF, DM, 32, 4);
  map2d_narrow(enc, &maps.wm, d_in[11], DM, NMOD, 256);
  Ptrs p;
  p.x = (const __nv_bfloat16*)d_in[0];
  p.w_r = (const __nv_bfloat16*)d_in[6];
  p.w_gate = (const __nv_bfloat16*)d_in[7];
  p.w_up = (const __nv_bfloat16*)d_in[8];
  p.w_down = (const __nv_bfloat16*)d_in[9];
  p.c = (const __nv_bfloat16*)d_in[10];
  p.w_mod = (const __nv_bfloat16*)d_in[11];
  p.out = (__nv_bfloat16*)d_out;
  fused_kernel<<<NMAIN + NHELP, 384, SMEM_BYTES>>>(maps, p);
}
```

```cpp
#include <cuda_runtime.h>
#include <cuda_bf16.h>
#include <cuda.h>
#include <stdint.h>
#include <type_traits>

#define HD 2
#define HDX 2
#define NRS 8
#define FPACE 3
#define GOST 20
#define WB 2
#define WN 20
#define RES0 17
#define RES1 20
#define HU 32
#define NS1 5
#define PG0 15
#define PSL 0
#define PPOS 2
#define FB0 0
#define FB2 8
#define OPS 8192
#define OFL 0
#define ODS 8
#define MODUL hfma2
#define ODS1 5
#define LD1 0
#define LD2 4
#define FB1 2
#define FPB 0
#define FPACE0 2
#define VREL 5
#define E0 3

namespace {

constexpr int SEQ = 2048, DM = 1024, NQ = 4096, SK = 2048, WIN = 512, FF = 3584, NMOD = 6144;
constexpr int NMAIN = 128, NHELP = 4, NFFN = 112;
constexpr int NSLOT = 4, SLOT_BYTES = 32768, UNIT = 16384, GST_BYTES = 3 * UNIT;
constexpr uint32_t XT1 = 0xDCBA, XT2 = 0x9687;
constexpr uint32_t WT0 = 0xA741, WT1 = 0x7420, WT2 = 0x4A20;
constexpr uint32_t AT0 = WT1, AT1 = WT2;
constexpr uint32_t QT = 0xDC9696DC;
constexpr int OFF_STAGE = 12 * UNIT;
constexpr uint32_t FT_G = 0x07B3, FT_U = 0xA628, FT_D = 0x5149;
constexpr int OFF_RES = 12 * UNIT;
constexpr int OFF_PAR = 14 * UNIT;
constexpr int OFF_BAR = OFF_PAR + 2528;
constexpr int SMEM_BYTES = OFF_BAR + 544;
static_assert(SMEM_BYTES <= 232448, "smem");

constexpr int PAR_T1 = 0;
constexpr int PAR_T2 = 512;
constexpr int PAR_CONST = 1536;
constexpr int PAR_RED = 1600;
constexpr int PAR_SINK = 2176;

struct Maps {
  CUtensorMap x, wq, k, v, wo, wg, wu, wd, wm, out;
};
struct Ptrs {
  const __nv_bfloat16 *x, *w_r, *c, *w_mod, *w_gate, *w_up, *w_down;
  __nv_bfloat16* out;
};

__device__ __align__(1024) uint8_t g_act[16 * 80 * UNIT];
__device__ __align__(128) uint32_t g_mod[NMOD];
__device__ __align__(128) uint32_t g_modp[2 * 2 * DM];
__device__ __align__(128) uint32_t g_ln1[SEQ * 4];
__device__ __align__(128) uint32_t g_cnt_h[16 * 32];
__device__ __align__(128) uint32_t g_cnt_o[128 * 32];
__device__ __align__(128) uint32_t g_xch[NMAIN * 8 * 256 * 4];
__device__ __align__(128) uint32_t g_stats[8 * SEQ * 4];
__device__ __align__(128) uint32_t g_cand[32];
__device__ __align__(128) uint32_t g_row[16 * 2 * DM];
__device__ __align__(128) uint32_t g_ypart[NMAIN * NFFN * 8];
__device__ uint32_t g_epoch;

__device__ __forceinline__ uint32_t fresh_lane() { uint32_t l; asm volatile("mov.u32 %0, %%laneid;" : "=r"(l)); return l; }
__device__ __forceinline__ uint32_t frag_offset(int warp) {
  const uint32_t l = fresh_lane();
  return ((warp & 3) * 16 + (l & 15)) * 128 + (((l >> 4) ^ (l & 7)) << 4);
}
__device__ __forceinline__ bool elect_one() {
  uint32_t p;
  asm volatile("{ .reg .pred q; elect.sync _|q, 0xffffffff; selp.u32 %0, 1, 0, q; }" : "=r"(p));
  return p;
}
__device__ __forceinline__ uint32_t smem_u32(const void* p) { return (uint32_t)__cvta_generic_to_shared(p); }
__device__ __forceinline__ void mbar_init(uint32_t bar, uint32_t cnt) {
  asm volatile("mbarrier.init.shared::cta.b64 [%0], %1;" ::"r"(bar), "r"(cnt) : "memory");
}
__device__ __forceinline__ void mbar_expect_tx(uint32_t bar, uint32_t bytes) {
  asm volatile("mbarrier.arrive.expect_tx.shared::cta.b64 _, [%0], %1;" ::"r"(bar), "r"(bytes) : "memory");
}
__device__ __forceinline__ void mbar_arrive(uint32_t bar) {
  asm volatile("mbarrier.arrive.shared::cta.b64 _, [%0];" ::"r"(bar) : "memory");
}
__device__ __forceinline__ void mbar_arrive_pred(uint32_t bar, bool p) {
  asm volatile("{ .reg .pred p; setp.ne.b32 p, %1, 0; @p mbarrier.arrive.shared::cta.b64 _, [%0]; }" ::"r"(bar), "r"((int)p) : "memory");
}
__device__ __forceinline__ void mbar_arrive_cl(uint32_t bar, uint32_t off, bool p = true) {
  asm volatile("{ .reg .pred p, q; .reg .b32 a; setp.ne.b32 q, %2, 0; setp.ne.and.b32 p, %0, 0, q; add.u32 a, %0, %1; @p mbarrier.arrive.shared::cluster.b64 _, [a]; }"
               ::"r"(bar), "r"(off), "r"((int)p) : "memory");
}
__device__ __forceinline__ uint32_t mapa(uint32_t addr, uint32_t cta) {
  uint32_t r; asm("mapa.shared::cluster.u32 %0, %1, %2;" : "=r"(r) : "r"(addr), "r"(cta)); return r;
}
__device__ __forceinline__ void cluster_arrive() { asm volatile("barrier.cluster.arrive.relaxed.aligned;" ::: "memory"); }
__device__ __forceinline__ void cluster_wait() { asm volatile("barrier.cluster.wait.aligned;" ::: "memory"); }
__device__ __forceinline__ void watchdog(uint32_t& n) {
}
__device__ __forceinline__ void mbar_wait(uint32_t bar, uint32_t parity) {
  asm volatile("{\n.reg .pred p;\nWAIT_%=:\nmbarrier.try_wait.parity.shared::cta.b64 p, [%0], %1;\n@!p bra WAIT_%=;\n}" ::"r"(bar), "r"(parity) : "memory");
}
__device__ __forceinline__ bool mbar_test(uint32_t bar, uint32_t parity) {
  uint32_t ok;
  asm volatile("{\n.reg .pred p;\nmbarrier.test_wait.parity.shared::cta.b64 p, [%1], %2;\nselp.u32 %0, 1, 0, p;\n}" : "=r"(ok) : "r"(bar), "r"(parity) : "memory");
  return ok;
}
__device__ __forceinline__ uint64_t l2_stream() {
  uint64_t f; asm("createpolicy.fractional.L2::evict_first.b64 %0, 1.0;" : "=l"(f)); return f;
}
__device__ __forceinline__ void tma2d(uint32_t dst, const CUtensorMap* m, int c0, int c1, uint32_t bar) {
  asm volatile("cp.async.bulk.tensor.2d.shared::cluster.global.mbarrier::complete_tx::bytes.L2::cache_hint [%0], [%1, {%3, %4}], [%2], %5;"
               ::"r"(dst), "l"(m), "r"(bar), "r"(c0), "r"(c1), "l"(l2_stream()) : "memory");
}
__device__ __forceinline__ void bulk_load(uint32_t dst, const void* src, uint32_t bytes, uint32_t bar) {
  asm volatile("cp.async.bulk.shared::cluster.global.mbarrier::complete_tx::bytes [%0], [%1], %2, [%3];" ::"r"(dst), "l"(src), "r"(bytes), "r"(bar) : "memory");
}
__device__ __forceinline__ void bulk_load_stream(uint32_t dst, const void* src, uint32_t bytes, uint32_t bar) {
  asm volatile("cp.async.bulk.shared::cluster.global.mbarrier::complete_tx::bytes.L2::cache_hint [%0], [%1], %2, [%3], %4;"
               ::"r"(dst), "l"(src), "r"(bytes), "r"(bar), "l"(l2_stream()) : "memory");
}
__device__ __forceinline__ void tma2d_store(const CUtensorMap* m, uint32_t src, int c0, int c1) {
  asm volatile("cp.async.bulk.tensor.2d.global.shared::cta.bulk_group [%0, {%2, %3}], [%1];" ::"l"(m), "r"(src), "r"(c0), "r"(c1) : "memory");
}
__device__ __forceinline__ void bulk_store(void* dst, uint32_t src, uint32_t bytes) {
  asm volatile("cp.async.bulk.global.shared::cta.bulk_group [%0], [%1], %2;" ::"l"(dst), "r"(src), "r"(bytes) : "memory");
}
__device__ __forceinline__ uint32_t unit_of(uint32_t table, uint32_t i) { return ((table >> (i * 4)) & 15) * UNIT; }
__device__ __forceinline__ void tma3d(uint32_t dst, const CUtensorMap* m, int c0, int c1, int c2, uint32_t bar) {
  asm volatile("cp.async.bulk.tensor.3d.shared::cluster.global.mbarrier::complete_tx::bytes.L2::cache_hint [%0], [%1, {%3, %4, %5}], [%2], %6;"
               ::"r"(dst), "l"(m), "r"(bar), "r"(c0), "r"(c1), "r"(c2), "l"(l2_stream()) : "memory");
}
template <bool STREAM>
__device__ __forceinline__ void tma3d_mc(uint32_t dst, const CUtensorMap* m, int c0, int c1, int c2, uint32_t bar) {
  if (STREAM)
    asm volatile("cp.async.bulk.tensor.3d.shared::cluster.global.mbarrier::complete_tx::bytes.multicast::cluster.L2::cache_hint [%0], [%1, {%3, %4, %5}], [%2], %6, %7;"
                 ::"r"(dst), "l"(m), "r"(bar), "r"(c0), "r"(c1), "r"(c2), "h"((uint16_t)3), "l"(l2_stream()) : "memory");
  else
    asm volatile("cp.async.bulk.tensor.3d.shared::cluster.global.mbarrier::complete_tx::bytes.multicast::cluster [%0], [%1, {%3, %4, %5}], [%2], %6;"
                 ::"r"(dst), "l"(m), "r"(bar), "r"(c0), "r"(c1), "r"(c2), "h"((uint16_t)3) : "memory");
}
__device__ __forceinline__ void prefetch_map(const CUtensorMap* m) {
  asm volatile("prefetch.tensormap [%0];" ::"l"(m) : "memory");
}
__device__ __forceinline__ void fence_async() { asm volatile("fence.proxy.async.global;" ::: "memory"); }
__device__ __forceinline__ void fence_async_smem() { asm volatile("fence.proxy.async.shared::cta;" ::: "memory"); }
__device__ __forceinline__ void bar_sync(int id, int n) { asm volatile("bar.sync %0, %1;" ::"r"(id), "r"(n) : "memory"); }
__device__ __forceinline__ void bar_arrive(int id, int n) { asm volatile("bar.arrive %0, %1;" ::"r"(id), "r"(n) : "memory"); }
__device__ __forceinline__ void wg_fence() { asm volatile("wgmma.fence.sync.aligned;" ::: "memory"); }
__device__ __forceinline__ void wg_commit() { asm volatile("wgmma.commit_group.sync.aligned;" ::: "memory"); }
template <int N> __device__ __forceinline__ void wg_wait() { asm volatile("wgmma.wait_group.sync.aligned %0;" ::"n"(N) : "memory"); }
__device__ __forceinline__ uint64_t make_desc(uint32_t addr, uint32_t lbo, uint32_t sbo) {
  return (uint64_t)((addr & 0x3FFFF) >> 4) | ((uint64_t)(lbo >> 4) << 16) | ((uint64_t)(sbo >> 4) << 32) | (1ull << 62);
}
__device__ __forceinline__ uint32_t ld_relaxed(const uint32_t* p) {
  uint32_t v; asm volatile("ld.relaxed.gpu.global.u32 %0, [%1];" : "=r"(v) : "l"(p) : "memory"); return v;
}
__device__ __forceinline__ uint32_t ld_acquire(const uint32_t* p) {
  uint32_t v; asm volatile("ld.acquire.gpu.global.u32 %0, [%1];" : "=r"(v) : "l"(p) : "memory"); return v;
}
__device__ __forceinline__ uint4 ld_relaxed4(const uint32_t* p) {
  uint4 v; asm volatile("ld.relaxed.gpu.global.v4.u32 {%0,%1,%2,%3}, [%4];" : "=r"(v.x), "=r"(v.y), "=r"(v.z), "=r"(v.w) : "l"(p) : "memory"); return v;
}
__device__ __forceinline__ uint2 ld_relaxed2(const uint32_t* p) {
  uint2 v; asm volatile("ld.relaxed.gpu.global.v2.u32 {%0,%1}, [%2];" : "=r"(v.x), "=r"(v.y) : "l"(p) : "memory"); return v;
}
__device__ __forceinline__ void st_relaxed(uint32_t* p, uint32_t v) {
  asm volatile("st.relaxed.gpu.global.u32 [%0], %1;" ::"l"(p), "r"(v) : "memory");
}
__device__ __forceinline__ void st_relaxed2(uint32_t* p, uint32_t a, uint32_t b) {
  asm volatile("st.relaxed.gpu.global.v2.u32 [%0], {%1,%2};" ::"l"(p), "r"(a), "r"(b) : "memory");
}
__device__ __forceinline__ void st_relaxed4(uint32_t* p, uint32_t a, uint32_t b, uint32_t c, uint32_t d) {
  asm volatile("st.relaxed.gpu.global.v4.u32 [%0], {%1,%2,%3,%4};" ::"l"(p), "r"(a), "r"(b), "r"(c), "r"(d) : "memory");
}
__device__ __forceinline__ void st_b128(uint32_t* p, uint32_t a, uint32_t b, uint32_t c, uint32_t d) {
  asm volatile("{ .reg .b64 u, v; .reg .b128 w; mov.b64 u, {%1, %2}; mov.b64 v, {%3, %4}; mov.b128 w, {u, v}; st.relaxed.gpu.global.b128 [%0], w; }"
               ::"l"(p), "r"(a), "r"(b), "r"(c), "r"(d) : "memory");
}
__device__ __forceinline__ uint4 ld_b128(const uint32_t* p) {
  uint4 r;
  asm volatile("{ .reg .b64 u, v; .reg .b128 w; ld.relaxed.gpu.global.b128 w, [%4]; mov.b128 {u, v}, w; mov.b64 {%0, %1}, u; mov.b64 {%2, %3}, v; }"
               : "=r"(r.x), "=r"(r.y), "=r"(r.z), "=r"(r.w) : "l"(p) : "memory");
  return r;
}
__device__ __forceinline__ void st_pairs(uint32_t* p, uint32_t a, uint32_t b, uint32_t tag) {
  asm volatile("{ .reg .b64 u, v; mov.b64 u, {%1, %3}; mov.b64 v, {%2, %3}; st.relaxed.gpu.global.v2.b64 [%0], {u, v}; }"
               ::"l"(p), "r"(a), "r"(b), "r"(tag) : "memory");
}
__device__ __forceinline__ uint4 ld_pairs(const uint32_t* p) {
  uint4 v;
  asm volatile("{ .reg .b64 u, v; ld.relaxed.gpu.global.v2.b64 {u, v}, [%4]; mov.b64 {%0, %1}, u; mov.b64 {%2, %3}, v; }"
               : "=r"(v.x), "=r"(v.y), "=r"(v.z), "=r"(v.w) : "l"(p) : "memory");
  return v;
}
__device__ __forceinline__ uint2 ld_pair(const uint32_t* p) {
  uint2 v;
  asm volatile("{ .reg .b64 u; ld.relaxed.gpu.global.b64 u, [%2]; mov.b64 {%0, %1}, u; }" : "=r"(v.x), "=r"(v.y) : "l"(p) : "memory");
  return v;
}
__device__ __forceinline__ void red_release(uint32_t* p, uint32_t v) {
  asm volatile("red.release.gpu.global.add.u32 [%0], %1;" ::"l"(p), "r"(v) : "memory");
}
__device__ __forceinline__ uint32_t ldg_nc1(const void* p) {
  uint32_t v;
  asm volatile("ld.global.nc.u32 %0, [%1];" : "=r"(v) : "l"(p));
  return v;
}
__device__ __forceinline__ uint4 ldg_nc4(const void* p) {
  uint4 v; asm volatile("ld.global.nc.L1::no_allocate.v4.u32 {%0,%1,%2,%3}, [%4];" : "=r"(v.x), "=r"(v.y), "=r"(v.z), "=r"(v.w) : "l"(p)); return v;
}
__device__ __forceinline__ uint4 ldg_stream4(const void* p) {
  uint4 v;
  asm volatile("ld.global.nc.L1::no_allocate.L2::cache_hint.v4.u32 {%0,%1,%2,%3}, [%4], %5;" : "=r"(v.x), "=r"(v.y), "=r"(v.z), "=r"(v.w) : "l"(p), "l"(l2_stream()));
  return v;
}
__device__ __forceinline__ void stg4(void* p, uint4 v) {
  asm volatile("st.global.v4.u32 [%0], {%1,%2,%3,%4};" ::"l"(p), "r"(v.x), "r"(v.y), "r"(v.z), "r"(v.w) : "memory");
}
__device__ __forceinline__ void wait_counter(const uint32_t* p, uint32_t target) {
  uint32_t n = 0;
  while (__any_sync(0xffffffffu, (int)(ld_acquire(p) - target) < 0)) { watchdog(n); }
}
__device__ __forceinline__ uint32_t tagf(float v, uint32_t tag) { return (__float_as_uint(v) & ~3u) | tag; }
__device__ __forceinline__ bool tag_ok(uint4 v, uint32_t tag) { return (((v.x ^ tag) | (v.y ^ tag) | (v.z ^ tag) | (v.w ^ tag)) & 3u) == 0; }
__device__ __forceinline__ float untag_sum(uint32_t a, uint32_t b) { return __uint_as_float(a & ~3u) + __uint_as_float(b & ~3u); }
__device__ __forceinline__ uint4 poll4(const uint32_t* p, uint32_t tag) {
  uint4 v = ld_relaxed4(p);
  uint32_t n = 0;
  while (!__all_sync(0xffffffffu, tag_ok(v, tag))) { v = ld_relaxed4(p); watchdog(n); }
  return v;
}
__device__ __forceinline__ float bf_lo(uint32_t v) { return __uint_as_float(v << 16); }
__device__ __forceinline__ float bf_hi(uint32_t v) { return __uint_as_float(v & 0xffff0000u); }
__device__ __forceinline__ uint32_t pack_bf(float lo, float hi) {
  uint32_t r; asm("cvt.rn.bf16x2.f32 %0, %1, %2;" : "=r"(r) : "f"(hi), "f"(lo)); return r;
}
__device__ __forceinline__ float rbf(float v) { return __uint_as_float(pack_bf(0.f, v) & 0xffff0000u); }
__device__ __forceinline__ uint32_t hmul2(uint32_t a, uint32_t b) {
  uint32_t r; asm("mul.rn.bf16x2 %0, %1, %2;" : "=r"(r) : "r"(a), "r"(b)); return r;
}
__device__ __forceinline__ uint32_t hadd2(uint32_t a, uint32_t b) {
  uint32_t r; asm("add.rn.bf16x2 %0, %1, %2;" : "=r"(r) : "r"(a), "r"(b)); return r;
}
__device__ __forceinline__ uint32_t hsub2(uint32_t a, uint32_t b) {
  uint32_t r; asm("sub.rn.bf16x2 %0, %1, %2;" : "=r"(r) : "r"(a), "r"(b)); return r;
}
__device__ __forceinline__ uint32_t hmax2(uint32_t a, uint32_t b) {
  uint32_t r; asm("max.bf16x2 %0, %1, %2;" : "=r"(r) : "r"(a), "r"(b)); return r;
}
__device__ __forceinline__ float rcp(float x) { float r; asm("rcp.approx.ftz.f32 %0, %1;" : "=f"(r) : "f"(x)); return r; }
__device__ __forceinline__ float ex2(float x) { float r; asm("ex2.approx.ftz.f32 %0, %1;" : "=f"(r) : "f"(x)); return r; }
__device__ __forceinline__ void stmatrix4(uint32_t addr, uint32_t a, uint32_t b, uint32_t c, uint32_t d) {
  asm volatile("stmatrix.sync.aligned.m8n8.x4.shared.b16 [%0], {%1,%2,%3,%4};" ::"r"(addr), "r"(a), "r"(b), "r"(c), "r"(d) : "memory");
}
__device__ __forceinline__ void ldmatrix4(uint32_t addr, uint32_t& a, uint32_t& b, uint32_t& c, uint32_t& d) {
  asm volatile("ldmatrix.sync.aligned.m8n8.x4.shared.b16 {%0,%1,%2,%3}, [%4];" : "=r"(a), "=r"(b), "=r"(c), "=r"(d) : "r"(addr) : "memory");
}
__device__ __forceinline__ void ldmatrix4t(uint32_t addr, uint32_t& a, uint32_t& b, uint32_t& c, uint32_t& d) {
  asm volatile("ldmatrix.sync.aligned.m8n8.x4.trans.shared.b16 {%0,%1,%2,%3}, [%4];" : "=r"(a), "=r"(b), "=r"(c), "=r"(d) : "r"(addr) : "memory");
}
__device__ __forceinline__ void mma16816(float (&d)[4], uint32_t a0, uint32_t a1, uint32_t a2, uint32_t a3, uint32_t b0, uint32_t b1) {
  asm volatile("mma.sync.aligned.m16n8k16.row.col.f32.bf16.bf16.f32 {%0,%1,%2,%3}, {%4,%5,%6,%7}, {%8,%9}, {%0,%1,%2,%3};"
               : "+f"(d[0]), "+f"(d[1]), "+f"(d[2]), "+f"(d[3]) : "r"(a0), "r"(a1), "r"(a2), "r"(a3), "r"(b0), "r"(b1));
}
__device__ __forceinline__ void sts1(uint32_t a, uint32_t v) { asm volatile("st.shared.u32 [%0], %1;" ::"r"(a), "r"(v) : "memory"); }
__device__ __forceinline__ uint4 lds4(uint32_t a) {
  uint4 v; asm volatile("ld.shared.v4.u32 {%0,%1,%2,%3}, [%4];" : "=r"(v.x), "=r"(v.y), "=r"(v.z), "=r"(v.w) : "r"(a) : "memory"); return v;
}
__device__ __forceinline__ uint2 lds2(uint32_t a) {
  uint2 v; asm volatile("ld.shared.v2.u32 {%0,%1}, [%2];" : "=r"(v.x), "=r"(v.y) : "r"(a) : "memory"); return v;
}
__device__ __forceinline__ uint32_t lds1(uint32_t a) {
  uint32_t v; asm volatile("ld.shared.u32 %0, [%1];" : "=r"(v) : "r"(a) : "memory"); return v;
}
__device__ __forceinline__ void sts2(uint32_t a, uint32_t x, uint32_t y) { asm volatile("st.shared.v2.u32 [%0], {%1,%2};" ::"r"(a), "r"(x), "r"(y) : "memory"); }
__device__ __forceinline__ void sts4(uint32_t a, uint4 v) {
  asm volatile("st.shared.v4.u32 [%0], {%1,%2,%3,%4};" ::"r"(a), "r"(v.x), "r"(v.y), "r"(v.z), "r"(v.w) : "memory");
}
__device__ __forceinline__ float silu_f(float v) { return __fdividef(v, 1.f + __expf(-v)); }
__device__ __forceinline__ uint32_t hfma2(uint32_t a, uint32_t b, uint32_t c) {
  uint32_t r; asm("fma.rn.bf16x2 %0, %1, %2, %3;" : "=r"(r) : "r"(a), "r"(b), "r"(c)); return r;
}
__device__ __forceinline__ void split_inv(float sd, uint32_t& ih, uint32_t& il) {
  const float inv = rcp(sd);
  ih = pack_bf(inv, inv);
  const float lo = inv - bf_lo(ih);
  il = pack_bf(lo, lo);
}
__device__ __forceinline__ uint32_t ln_norm(uint32_t x, uint32_t mean2, uint32_t ih, uint32_t il) {
  const uint32_t d = hsub2(x, mean2);
  return hfma2(d, ih, hmul2(d, il));
}
__device__ __forceinline__ uint32_t modul(uint32_t n, uint32_t c1, uint32_t sh) { return hadd2(hmul2(n, c1), sh); }
__device__ __forceinline__ uint32_t ln_mod(uint32_t x, uint32_t mean2, uint32_t ih, uint32_t il, uint32_t c1, uint32_t sh) {
  return modul(ln_norm(x, mean2, ih, il), c1, sh);
}

#define R8(a, i) "+f"(a[i]), "+f"(a[i + 1]), "+f"(a[i + 2]), "+f"(a[i + 3]), "+f"(a[i + 4]), "+f"(a[i + 5]), "+f"(a[i + 6]), "+f"(a[i + 7])
#define D64 "{%0,%1,%2,%3,%4,%5,%6,%7,%8,%9,%10,%11,%12,%13,%14,%15,%16,%17,%18,%19,%20,%21,%22,%23,%24,%25,%26,%27,%28,%29,%30,%31," \
            "%32,%33,%34,%35,%36,%37,%38,%39,%40,%41,%42,%43,%44,%45,%46,%47,%48,%49,%50,%51,%52,%53,%54,%55,%56,%57,%58,%59,%60,%61,%62,%63}"
template <int TB>
__device__ __forceinline__ void mma_ss(float (&d)[64], uint64_t da, uint64_t db, int sc) {
  asm volatile("{\n.reg .pred p;\nsetp.ne.b32 p, %66, 0;\n"
               "wgmma.mma_async.sync.aligned.m64n128k16.f32.bf16.bf16 " D64 ", %64, %65, p, 1, 1, 0, %67;\n}"
               : R8(d, 0), R8(d, 8), R8(d, 16), R8(d, 24), R8(d, 32), R8(d, 40), R8(d, 48), R8(d, 56)
               : "l"(da), "l"(db), "r"(sc), "n"(TB));
}
template <int TB>
__device__ __forceinline__ void mma_rs(float (&d)[64], uint32_t a0, uint32_t a1, uint32_t a2, uint32_t a3, uint64_t db, int sc) {
  asm volatile("{\n.reg .pred p;\nsetp.ne.b32 p, %69, 0;\n"
               "wgmma.mma_async.sync.aligned.m64n128k16.f32.bf16.bf16 " D64 ", {%64,%65,%66,%67}, %68, p, 1, 1, %70;\n}"
               : R8(d, 0), R8(d, 8), R8(d, 16), R8(d, 24), R8(d, 32), R8(d, 40), R8(d, 48), R8(d, 56)
               : "r"(a0), "r"(a1), "r"(a2), "r"(a3), "l"(db), "r"(sc), "n"(TB));
}
#define D128 "{%0,%1,%2,%3,%4,%5,%6,%7,%8,%9,%10,%11,%12,%13,%14,%15,%16,%17,%18,%19,%20,%21,%22,%23,%24,%25,%26,%27,%28,%29,%30,%31," \
             "%32,%33,%34,%35,%36,%37,%38,%39,%40,%41,%42,%43,%44,%45,%46,%47,%48,%49,%50,%51,%52,%53,%54,%55,%56,%57,%58,%59,%60,%61,%62,%63," \
             "%64,%65,%66,%67,%68,%69,%70,%71,%72,%73,%74,%75,%76,%77,%78,%79,%80,%81,%82,%83,%84,%85,%86,%87,%88,%89,%90,%91,%92,%93,%94,%95," \
             "%96,%97,%98,%99,%100,%101,%102,%103,%104,%105,%106,%107,%108,%109,%110,%111,%112,%113,%114,%115,%116,%117,%118,%119,%120,%121,%122,%123,%124,%125,%126,%127}"
#define R128(d, e) R8(d, 0), R8(d, 8), R8(d, 16), R8(d, 24), R8(d, 32), R8(d, 40), R8(d, 48), R8(d, 56), \
                   R8(e, 0), R8(e, 8), R8(e, 16), R8(e, 24), R8(e, 32), R8(e, 40), R8(e, 48), R8(e, 56)
__device__ __forceinline__ void mma256_ss(float (&d)[64], float (&e)[64], uint64_t da, uint64_t db, int sc) {
  asm volatile("{\n.reg .pred p;\nsetp.ne.b32 p, %130, 0;\n"
               "wgmma.mma_async.sync.aligned.m64n256k16.f32.bf16.bf16 " D128 ", %128, %129, p, 1, 1, 0, 1;\n}"
               : R128(d, e) : "l"(da), "l"(db), "r"(sc));
}
__device__ __forceinline__ void mma256_rs(float (&d)[64], float (&e)[64], uint32_t a0, uint32_t a1, uint32_t a2, uint32_t a3, uint64_t db) {
  asm volatile("{\n.reg .pred p;\nsetp.ne.b32 p, 1, 0;\n"
               "wgmma.mma_async.sync.aligned.m64n256k16.f32.bf16.bf16 " D128 ", {%128,%129,%130,%131}, %132, p, 1, 1, 1;\n}"
               : R128(d, e) : "r"(a0), "r"(a1), "r"(a2), "r"(a3), "l"(db));
}
template <int N> __device__ __forceinline__ void keep(float (&a)[N]) {
#pragma unroll
  for (int i = 0; i < N; i++) asm volatile("" : "+f"(a[i])::"memory");
}
template <int N> __device__ __forceinline__ void keep(uint32_t (&a)[N]) {
#pragma unroll
  for (int i = 0; i < N; i++) asm volatile("" : "+r"(a[i])::"memory");
}

#define STAMP(idx) do {} while (0)
#define PROF(grp, cond, idx) do {} while (0)

constexpr float SCL2 = 1.4426950408889634f * 0.08838834764831845f;

__device__ __forceinline__ void pack_p(const float (&s)[64], uint32_t (&p)[32]) {
#pragma unroll
  for (int i = 0; i < 32; i++) p[i] = pack_bf(s[2 * i], s[2 * i + 1]);
}

__device__ __forceinline__ void issue_qk(float (&s)[64], uint32_t q0, uint32_t q1, uint32_t kslot) {
  const uint64_t db = make_desc(kslot, 16, 1024), da0 = make_desc(q0, 16, 1024), da1 = make_desc(q1, 16, 1024);
#pragma unroll
  for (int kk = 0; kk < 8; kk++) mma_ss<0>(s, (kk < 4 ? da0 : da1) + (kk & 3) * 2, db + (kk >> 2) * 1024 + (kk & 3) * 2, kk != 0);
}
__device__ __forceinline__ void issue_pv(float (&o)[64], uint32_t (&p)[32], uint32_t vslot, int acc) {
  uint64_t db = make_desc(vslot, 16384, 1024);
#pragma unroll
  for (int kk = 0; kk < 8; kk++)
    mma_rs<1>(o, p[4 * kk], p[4 * kk + 1], p[4 * kk + 2], p[4 * kk + 3], db + kk * 128, kk == 0 ? acc : 1);
}

template <int H>
__device__ __forceinline__ void store_chunk(const float (&a)[64], uint32_t addr) {
#pragma unroll
  for (int i = 8 * H; i < 8 * H + 8; i += 2)
    stmatrix4(addr ^ ((i & 7) << 4), pack_bf(a[4 * i], a[4 * i + 1]), pack_bf(a[4 * i + 2], a[4 * i + 3]),
              pack_bf(a[4 * i + 4], a[4 * i + 5]), pack_bf(a[4 * i + 6], a[4 * i + 7]));
}
template <int H>
__device__ __forceinline__ void store_chunk(const float (&a)[64], float i0, float i1, uint32_t addr) {
#pragma unroll
  for (int i = 8 * H; i < 8 * H + 8; i += 2)
    stmatrix4(addr ^ ((i & 7) << 4), pack_bf(a[4 * i] * i0, a[4 * i + 1] * i0), pack_bf(a[4 * i + 2] * i1, a[4 * i + 3] * i1),
              pack_bf(a[4 * i + 4] * i0, a[4 * i + 5] * i0), pack_bf(a[4 * i + 6] * i1, a[4 * i + 7] * i1));
}
__device__ __forceinline__ float inv_quad_sum(float l) {
  l += __shfl_xor_sync(0xffffffffu, l, 1);
  l += __shfl_xor_sync(0xffffffffu, l, 2);
  return rcp(l);
}

__device__ __forceinline__ void ln_scalars(float mean, float var, float& mb, float& sd) {
  mb = rbf(mean);
  float r; asm("sqrt.approx.ftz.f32 %0, %1;" : "=f"(r) : "f"(rbf(rbf(var) + 1e-5f)));
  sd = rbf(r);
}

__global__ void __cluster_dims__(2, 1, 1) __launch_bounds__(384, 1) fused_kernel(const __grid_constant__ Maps maps, const Ptrs P) {
  extern __shared__ __align__(1024) uint8_t smem_raw[];
  const uint32_t base = smem_u32(smem_raw);
  const int tid = threadIdx.x, lane = tid & 31;
  const int warp = __shfl_sync(0xffffffffu, tid >> 5, 0);
  const int b = blockIdx.x;
  PROF(31, tid == 0, 0);

  if (b >= NMAIN) {
    float* sc = reinterpret_cast<float*>(smem_raw);
    float* red = sc + DM;
    for (int k = tid; k < DM; k += 384) sc[k] = rbf(silu_f(__bfloat162float(P.c[k])));
    __syncthreads();
    if (tid < 256) {
      const int col = 2048 + (b - NMAIN) * 1024 + (tid & 127) * 8, r0 = (tid >> 7) * 512;
      float acc[8];
#pragma unroll
      for (int e = 0; e < 8; e++) acc[e] = 0.f;
#pragma unroll 1
      for (int r = r0; r < r0 + 512; r += HU) {
        uint4 w[HU];
#pragma unroll
        for (int u = 0; u < HU; u++) w[u] = ldg_stream4(P.w_mod + (size_t)(r + u) * NMOD + col);
#pragma unroll
        for (int u = 0; u < HU; u++) {
          float s = sc[r + u];
          acc[0] += s * bf_lo(w[u].x); acc[1] += s * bf_hi(w[u].x); acc[2] += s * bf_lo(w[u].y); acc[3] += s * bf_hi(w[u].y);
          acc[4] += s * bf_lo(w[u].z); acc[5] += s * bf_hi(w[u].z); acc[6] += s * bf_lo(w[u].w); acc[7] += s * bf_hi(w[u].w);
        }
      }
      if (tid >= 128) {
#pragma unroll
        for (int e = 0; e < 8; e++) red[(tid & 127) * 8 + e] = acc[e];
      }
      const uint32_t tag = ld_relaxed(&g_epoch) % 3 + 1;
      bar_sync(1, 256);
      if (tid < 128) {
        uint32_t o[8];
#pragma unroll
        for (int e = 0; e < 8; e++) o[e] = __float_as_uint(rbf(acc[e] + red[tid * 8 + e])) | tag;
        st_relaxed4(g_mod + col, o[0], o[1], o[2], o[3]);
        st_relaxed4(g_mod + col + 4, o[4], o[5], o[6], o[7]);
        const uint4 wr = ldg_nc4(P.w_r + tid * 8);
        const uint32_t wv[4] = {wr.x, wr.y, wr.z, wr.w};
        float dsum = 0.f;
#pragma unroll
        for (int e = 0; e < 8; e++) {
          const float m = bf_hi(o[e]);
          dsum += (b == NMAIN + 2 ? rbf(1.f + m) : m) * ((e & 1) ? bf_hi(wv[e >> 1]) : bf_lo(wv[e >> 1]));
        }
#pragma unroll
        for (int k = 16; k > 0; k >>= 1) dsum += __shfl_xor_sync(0xffffffffu, dsum, k);
        if (lane == 0) st_relaxed(g_mod + (b - NMAIN) * 4 + warp, tagf(dsum, tag));
      }
    }
    PROF(2, tid == 0, 1);
    return;
  }

  const int rank = b & 1;
  const int rb = ((b >> 4) << 1) | rank, cj = (b >> 1) & 7;
  const uint32_t bfull = base + OFF_BAR, bempty = bfull + NSLOT * 8;
  const uint32_t gfull = bempty + NSLOT * 8, gempty = gfull + 32;
  const uint32_t bar_ofull = gempty + 32;
  const uint32_t bar_ofree = bar_ofull + 32;
  const uint32_t bar_par = bar_ofree + 32;
  const uint32_t bar_mod = bar_par + 8;
  const uint32_t bar_pread = bar_mod + 8;
  const uint32_t bar_xres = bar_pread + 8;
  const uint32_t bar_ring = bar_xres + 8;
  const uint32_t bar_box = bar_ring + 24;
  const uint32_t bar_go = bar_box + 96;
  const uint32_t bar_go2 = bar_go + 16;
  const uint32_t bar_cnt = bar_go + 24;
  const uint32_t xfull = bar_go + 40, xempty = xfull + 32;
  const uint32_t bar_hw = xempty + 32, bar_hx = bar_hw + 8;
  const uint32_t bar_hpub = bar_hx + 16;
  const uint32_t bar_win = bar_hpub + 16;
  const uint32_t bar_rx = bar_win + 8;
  const uint32_t bar_sel = bar_rx + 8;
  const uint32_t bar_gate = bar_sel + 8;
  const uint32_t bar_rel = bar_gate + 8;
  const uint32_t bar_od = bar_rel + 8;
  const uint32_t bar_res = bar_go + 8;
  const uint32_t stage = base + OFF_STAGE, par = base + OFF_PAR;

  if (warp == 8 && elect_one()) {
    for (int s = 0; s < NSLOT; s++) { mbar_init(bfull + s * 8, 1); mbar_init(bempty + s * 8, 16); }
    for (int s = 0; s < 4; s++) { mbar_init(gfull + s * 8, 1); mbar_init(gempty + s * 8, 16); mbar_init(xfull + s * 8, 1); mbar_init(xempty + s * 8, 8); mbar_init(bar_ofree + s * 8, 1); mbar_init(bar_ofull + s * 8, 128); }
    mbar_init(bar_par, 64); mbar_init(bar_mod, 256); mbar_init(bar_pread, 2); mbar_init(bar_xres, 1);
    mbar_init(bar_ring, 8); mbar_init(bar_ring + 8, 8); mbar_init(bar_ring + 16, 8);
    mbar_init(bar_go, 1); mbar_init(bar_go2, 1); mbar_init(bar_cnt, 1); mbar_init(bar_cnt + 8, 1); mbar_init(bar_hpub, 8); mbar_init(bar_hpub + 8, 8); mbar_init(bar_res, 1); mbar_init(bar_win, 1); mbar_init(bar_rx, 1); mbar_init(bar_sel, 64); mbar_init(bar_gate, 8); mbar_init(bar_rel, 8); mbar_init(bar_od, 1);
    for (int s = 0; s < 12; s++) mbar_init(bar_box + s * 8, 1);
    asm volatile("fence.mbarrier_init.release.cluster;" ::: "memory");
    prefetch_map(&maps.x); prefetch_map(&maps.wq); prefetch_map(&maps.k); prefetch_map(&maps.v);
  }
  if (warp == 9 && elect_one()) {
    mbar_init(bar_hw, 1); mbar_init(bar_hx, 1); mbar_init(bar_hx + 8, 1);
    asm volatile("fence.mbarrier_init.release.cluster;" ::: "memory");
    mbar_expect_tx(bar_hw, 32768);
    mbar_expect_tx(bar_hx, 16384);
    mbar_expect_tx(bar_hx + 8, 16384);
    const __nv_bfloat16* xs = P.x + (size_t)(rb * 128 + cj * 16) * DM;
    bulk_load(base + 2 * GST_BYTES, xs, 16384, bar_hx);
    tma2d(stage, &maps.wm, (b >> 1) * 32, rank * 512, bar_hw);
    tma2d(stage + 16384, &maps.wm, (b >> 1) * 32, rank * 512 + 256, bar_hw);
    bulk_load(base + 3 * GST_BYTES, xs + 8 * DM, 16384, bar_hx + 8);
  }
  cluster_arrive();

  if (warp >= 8) {
    asm volatile("setmaxnreg.dec.sync.aligned.u32 40;");
    if (warp < 10) bar_arrive(1, 320);
    const uint32_t epoch = ld_relaxed(&g_epoch);
    cluster_wait();
    if (warp == 8) {
      const int kvrow = (cj >> 1) * SK + (SK - WIN);
      int wch = cj * 8 + rank * 2;
#pragma unroll 1
      for (int ps = 0; ps < 3; ps++) {
        const CUtensorMap* mw = ps == 2 ? &maps.wo : &maps.wq;
        const uint32_t xt = ps == 1 ? XT1 : XT2, wt = ps == 0 ? WT0 : (ps == 1 ? WT1 : WT2);
        const int nst = ps == 2 ? 32 : 16;
#pragma unroll 1
        for (int i = 0; i < nst; i++) {
          const uint32_t bf = gfull + (i & 3) * 8;
          const int kt = ps == 2 ? (((cj & 1) * 4 + ((i >> 1) & 3)) * 4 + (i >> 3)) * 2 + (i & 1) : (i + (ps ? 0 : b & 14)) & 15;
          const uint32_t wd = base + unit_of(wt, i & 3) + rank * UNIT, xd = base + unit_of(xt, i & 3);
          const uint8_t* xs = g_act + (uint32_t)(rb * 80 + (ps - 1) * 16 + kt) * UNIT;
          if (ps == 0 && i == HD) mbar_wait(bar_mod, 0);
          const bool xfirst = ps && i < 2;
          if (ps == 2 && i == 0) mbar_wait(bar_ofree + 24, 0);
          if (i == 0) fence_async();
          mbar_wait(gempty + (i & 3) * 8, ((i >> 2) & 1) ^ 1);
          if (elect_one()) {
            mbar_expect_tx(bf, ps ? GST_BYTES : 2 * UNIT);
            if (xfirst) bulk_load_stream(xd, xs, UNIT, bf);
          }
          if (ps && i < 4) mbar_wait(bempty + i * 8, 1);
          if (elect_one()) tma3d_mc<true>(wd, mw, 0, (i == 31 ? kt ^ (rank * 32) : kt) * 64, i == 31 ? cj * 2 : wch, bf);
          if (ps) {
            if (i == 16 || i == 24) { mbar_wait(bar_cnt + i - 16, 0); fence_async(); }
            if (i == RES0) mbar_wait(bar_res, 0);
            if (i == 2) mbar_wait(bar_ofree + (ps - 1) * 16, 0);
            if (elect_one()) {
              if (i == 31) bulk_load(xd, xs, UNIT, bf); else if (!xfirst) bulk_load_stream(xd, xs, UNIT, bf);
              mbar_arrive_pred(bar_go, i == GOST - 1);
              if (PG0 < 16) mbar_arrive_pred(bar_go2, ps == 1 && i == PG0);
              mbar_arrive_pred(bar_od, i == (ps == 1 ? ODS1 : ODS));
              if (i == RES0) mbar_expect_tx(bar_xres, 32768);
              if (i == RES0 || i == RES1) tma2d(base + OFF_RES + (i == RES1) * UNIT, &maps.x, cj * 128 + (i == RES1) * 64, rb * 128, bar_xres);
            }
          }
        }
        if (ps == 2) break;
        wch = ps ? ((wch >> 3) ^ rank) * 2 : wch + 4;
#pragma unroll 1
        for (int u = 0; u < 16; u++) {
          const bool isk = (u == 0) || ((u & 1) && u < 15);
          const int blk = (isk ? (u + 1) >> 1 : (u == 15 ? 7 : (u >> 1) - 1)) & 3;
          const uint32_t sl = base + unit_of(ps ? AT1 : AT0, u & 3) + rank * UNIT, bf = bfull + (u & 3) * 8;
          if (u < 4) mbar_wait(gempty + ((u + 1) >> 1) * 8, 1);
          mbar_wait(bempty + (u & 3) * 8, ((u >> 2) & 1) ^ 1);
          if (elect_one()) {
            mbar_arrive_pred(bar_go2, ps && u + 16 == PG0);
            mbar_expect_tx(bf, SLOT_BYTES);
            tma3d_mc<false>(sl, isk ? &maps.k : &maps.v, 0, kvrow + blk * 128, rank, bf);
          }
        }
      }
      if (elect_one()) mbar_expect_tx(bar_rx, UNIT);
      mbar_wait(bar_rel, 0);
      if (elect_one()) {
        bulk_load_stream(base + UNIT, g_act + (uint32_t)(rb * 80 + 16 + 63 - (cj & 1) * 32) * UNIT, UNIT, bar_rx);
      }
      if (b < NFFN) {
#pragma unroll 1
        for (int u = 0; u < 12; u++) {
          const uint32_t dst = base + unit_of(u < 4 ? FT_G : (u < 8 ? FT_U : FT_D), u & 3);
          if (elect_one()) mbar_expect_tx(bar_box + u * 8, UNIT);
          if (u == FB0 || u == FB1 || u == FB2) mbar_wait(bar_ring + (u == FB2 ? 16 : u == FB1 ? 8 : 0), 0);
          const int fp = u < FPB ? FPACE0 : FPACE;
          if (u >= fp) mbar_wait(bar_box + (u - fp) * 8, 0);
          if (elect_one()) {
            if (u < 8) tma2d(dst, u < 4 ? &maps.wg : &maps.wu, b * 32, (u & 3) * 256, bar_box + u * 8);
            else tma3d(dst, &maps.wd, 0, b * 32, (u - 8) * 4, bar_box + u * 8);
          }
        }
      }
    } else if (warp == 9) {
      const uint32_t target = 8 * (epoch + 1);
      uint32_t hmask = 0;
#pragma unroll 1
      for (int i = 0; i < 16; i++) {
        if (i == HDX) mbar_wait(bar_mod, 0);
        const uint32_t need = i == 15 ? 0xffffu : 1u << ((2 * cj + i) & 15);
        if (i >= NRS && (hmask & need) != need) {
          uint32_t n = 0;
          do { hmask = __ballot_sync(0xffffffffu, ld_acquire(&g_cnt_h[rb * 32 + (lane & 15)]) == epoch + 1); watchdog(n); } while ((hmask & need) != need);
          PROF(1, lane == 0 && i == NRS, 26);
          fence_async();
        }
        mbar_wait(xempty + (i & 3) * 8, ((i >> 2) & 1) ^ 1);
        if (elect_one()) {
          mbar_expect_tx(xfull + (i & 3) * 8, UNIT);
          if (i < NRS) tma2d(base + (i & 3) * GST_BYTES, &maps.x, ((2 * cj + i) & 15) * 64, rb * 128, xfull + (i & 3) * 8);
          else bulk_load_stream(base + (i & 3) * GST_BYTES, g_act + (uint32_t)(rb * 80 + ((2 * cj + i) & 15)) * UNIT, UNIT, xfull + (i & 3) * 8);
        }
      }
      prefetch_map(&maps.wo);
#pragma unroll 1
      for (int t = 0; t < 4; t++) {
        if (t & 1) mbar_wait(bar_od, t >> 1);
#pragma unroll 1
        for (int p = 0; p < 32768 / OPS; p++) {
          const uint32_t w = p / (16384 / OPS), c = (p / (8192 / OPS)) & 1, off = w * 8192 + (p % (8192 / OPS)) * OPS;
          mbar_wait(bar_ofull + (t & 1) * 16 + w * 8, t >> 1);
          if (elect_one()) {
            bulk_store(g_act + (uint32_t)(rb * 80 + 16 + (cj * 4 + t) * 2 + c) * UNIT + off, base + unit_of(QT, 2 * t + c) + off, OPS);
            asm volatile("cp.async.bulk.commit_group;" ::: "memory");
            asm volatile("cp.async.bulk.wait_group.read %0;" ::"n"(OFL) : "memory");
          }
        }
        if (elect_one()) {
          asm volatile("cp.async.bulk.wait_group.read 0;" ::: "memory");
          mbar_arrive(t < 3 ? bar_ofree + t * 8 : bar_res);
          asm volatile("cp.async.bulk.wait_group 0;" ::: "memory");
          fence_async();
          red_release(&g_cnt_o[((rb * 4 + t) * 2 + (cj >> 2)) * 32], 2);
        }
        if (t) {
          wait_counter(&g_cnt_o[(rb * 8 + 2 * t + (cj & 1)) * 32], target);
          if (t & 1) wait_counter(&g_cnt_o[(rb * 8 + (t == 1 ? cj & 1 : 7 - (cj & 1))) * 32], target);
          if (elect_one()) mbar_arrive(t == 1 ? bar_ofree + 24 : bar_cnt + t * 8 - 16);
        }
      }
      PROF(2, lane == 0, 27);
      const uint32_t tag = epoch % 3 + 1;
      const uint32_t* inbox = g_cand + (lane & 15);
      mbar_wait(bar_ring + 16, 0);
      uint32_t c0 = ld_relaxed(inbox), n = 0;
#define CAND_STEP(cv)                                                                                        \
      {                                                                                                      \
        const bool valid = (cv & 3u) == tag, all = __all_sync(0xffffffffu, valid);                           \
        const uint32_t best = __reduce_max_sync(0xffffffffu, valid ? cv : 0u);                               \
        const uint32_t blk = __ffs(__ballot_sync(0xffffffffu, cv == best)) - 1;                              \
        if (best) sts2(par + PAR_CONST + 56, best, (blk << 7 | (~best >> 2 & 127)) | (all ? 0x1800 : 0x800)); \
        if (all) break;                                                                                      \
        cv = ld_relaxed(inbox);                                                                              \
      }
      while (true) { CAND_STEP(c0) watchdog(n); }
    } else {
      const int t2 = tid - 320;
      mbar_wait(bar_hpub + (warp & 1) * 8, 0);
      PROF(1, t2 == 0, 24);
#pragma unroll 1
      for (int c = 0; c < 8; c++) {
        const uint32_t off = (warp & 1) * UNIT + c * 2048 + lane * 16;
        uint8_t* dst = g_act + (uint32_t)(rb * 80 + cj * 2) * UNIT + off;
        const uint4 v0 = lds4(stage + off), v1 = lds4(stage + off + 512), v2 = lds4(stage + off + 1024), v3 = lds4(stage + off + 1536);
        stg4(dst, v0); stg4(dst + 512, v1); stg4(dst + 1024, v2); stg4(dst + 1536, v3);
      }
      __syncwarp();
      PROF(1, t2 == 0, 15);
      if (lane == 0) {
        mbar_arrive(bar_pread);
        red_release(&g_cnt_h[rb * 32 + cj * 2 + (warp & 1)], 1);
        PROF(1, t2 == 0, 25);
        prefetch_map(&maps.wg); prefetch_map(&maps.wu); prefetch_map(&maps.wd); prefetch_map(&maps.out);
      }
      __syncwarp();
      if (b < NFFN) {
        mbar_wait(bar_go2, 0);
        const __nv_bfloat16* pg = ((b & 1) ? P.w_up : P.w_gate) + (b >> 1) * 64 + (size_t)t2 * FF;
        const __nv_bfloat16* pd = P.w_down + (size_t)b * 32768 + t2 * 64;
        PROF(2, t2 == 0, 13);
#pragma unroll 1
        for (int i = 0; i < WN; i += WB) {
          uint32_t v[WB];
#pragma unroll
          for (int u = 0; u < WB; u++) {
            const int k = i + u;
            asm volatile("ld.global.cg.L2::128B.u32 %0, [%1];" : "=r"(v[u]) : "l"(k < 16 ? pg + (size_t)k * 64 * FF : pd + (k - 16) * 4096));
          }
#pragma unroll
          for (int u = 1; u < WB; u++) v[0] ^= v[u];
          sts1(par + PAR_SINK + t2 * 4, v[0]);
        }
        PROF(2, t2 == 0, 14);
      }
      const uint32_t tag = epoch % 3 + 1;
      mbar_wait(bar_go, 0);
      bar_sync(4, 64);
      if (warp == 10) {
        const uint32_t* src = g_mod + 2 * DM + cj * 128 + lane * 4;
        const uint2 wr = *reinterpret_cast<const uint2*>(P.w_r + cj * 128 + lane * 4);
        uint4 vga, vsb, vcb, vgb;
        uint32_t n = 0;
        do {
          vga = ld_relaxed4(src); vsb = ld_relaxed4(src + DM); vcb = ld_relaxed4(src + 2 * DM); vgb = ld_relaxed4(src + 3 * DM);
          watchdog(n);
        } while (!__all_sync(0xffffffffu, tag_ok(vga, tag) && tag_ok(vsb, tag) && tag_ok(vcb, tag) && tag_ok(vgb, tag)));
        const float c0 = rbf(1.f + bf_hi(vcb.x)), c1 = rbf(1.f + bf_hi(vcb.y)), c2 = rbf(1.f + bf_hi(vcb.z)), c3 = rbf(1.f + bf_hi(vcb.w));
        const float a0 = c0 * bf_lo(wr.x), a1 = c1 * bf_hi(wr.x), a2 = c2 * bf_lo(wr.y), a3 = c3 * bf_hi(wr.y);
        const uint32_t h0 = pack_bf(a0, a1), h1 = pack_bf(a2, a3);
        const uint32_t t1 = par + PAR_T1 + (lane >> 2) * 64 + (lane & 1) * 32 + (lane & 2) * 2;
        sts1(t1, h0); sts1(t1 + 8, pack_bf(a0 - bf_lo(h0), a1 - bf_hi(h0)));
        sts1(t1 + 16, h1); sts1(t1 + 24, pack_bf(a2 - bf_lo(h1), a3 - bf_hi(h1)));
        const uint32_t tg = par + PAR_SINK + (lane >> 3) * 64 + (lane & 1) * 32 + (lane & 6) * 2;
        sts1(tg, __byte_perm(vga.x, vga.y, 0x7632)); sts1(tg + 16, __byte_perm(vga.z, vga.w, 0x7632));
        sts4(par + PAR_T2 + lane * 32, make_uint4(pack_bf(c0, c1), __byte_perm(vsb.x, vsb.y, 0x7632), __byte_perm(vgb.x, vgb.y, 0x7632), __byte_perm(vga.x, vga.y, 0x7632)));
        sts4(par + PAR_T2 + lane * 32 + 16, make_uint4(pack_bf(c2, c3), __byte_perm(vsb.z, vsb.w, 0x7632), __byte_perm(vgb.z, vgb.w, 0x7632), __byte_perm(vga.z, vga.w, 0x7632)));
      } else {
        const uint4 g = poll4((lane & 2) ? g_mod + 8 - (lane & 1) * 4 : g_mod + 5 * DM + b * 8 + (lane & 1) * 4, tag);
        sts1(par + PAR_CONST + 60, 0);
        if (lane < 2) sts4(par + PAR_CONST + 16 + lane * 16, g);
        else if (lane < 4) sts2(par + PAR_CONST + (lane - 2) * 8, __float_as_uint(untag_sum(g.x, g.y) + untag_sum(g.z, g.w)), epoch);
      }
      __syncwarp();
#pragma unroll 4
      for (int q = 0; q < 32; q++) st_b128(g_xch + ((size_t)b * 8 * 256 + q * 64 + t2) * 4, (epoch & 1) << 16, 0, 0, 0);
      for (int q = 0; q < 2; q++) st_relaxed4(g_stats + ((size_t)cj * SEQ + rb * 128 + q * 64 + t2) * 4, 0, 0, 0, 0);
      if (b < NFFN)
        for (int q = 0; q < 4; q++) st_relaxed4(g_ypart + ((size_t)(q * 32 + (t2 >> 1)) * NFFN + b) * 8 + (t2 & 1) * 4, 0, 0, 0, 0);
      st_relaxed4(g_row + rb * 2 * DM + (t2 >> 5) * DM + cj * 128 + (t2 & 31) * 4, 0, 0, 0, 0);
      __threadfence();
      mbar_arrive(bar_par);
      mbar_wait(bar_gate, 0);
      uint32_t have = 0, n = 0;
      while (true) {
        const uint32_t st = lds1(par + PAR_CONST + 60) >> 7;
        if ((st & 31) != have) {
          const uint32_t* hsrc = g_row + (st & 15) * 2 * DM + t2 * 4;
          uint4 hv[4];
          bool ok = true;
#pragma unroll
          for (int i = 0; i < 4; i++) hv[i] = ld_pairs(hsrc + i * 256);
#pragma unroll
          for (int i = 0; i < 4; i++) {
            sts2(base + ((FT_G >> i * 4) & 15) * UNIT + (warp & 1) * 8192 + 256 + lane * 8, hv[i].x, hv[i].z);
            ok = ok && hv[i].y == tag && hv[i].w == tag;
          }
          have = __all_sync(0xffffffffu, ok) ? st & 31 : 0;
        }
        if ((st ^ have) == 32) break;
        watchdog(n);
      }
      mbar_arrive(bar_sel);
    }
    __syncwarp();
    cluster_arrive();
    {
      const uint32_t tag = epoch % 3 + 1, t3 = tid - 256;
      mbar_wait(bar_win, 0);
      uint2 win = lds2(par + PAR_CONST + 56);
      win.y &= 0x7ff;
      const uint32_t* fsrc = g_row + (win.y >> 7) * 2 * DM + (b >> 1) * 16 + (t3 & 3) * 4 + (b & 1) * 2;
      const uint32_t* ysrc = g_ypart + (size_t)b * NFFN * 8 + min(t3, NFFN - 1) * 4;
      uint2 fh = ld_pair(fsrc), fx = ld_pair(fsrc + DM);
      if (PSL) __nanosleep(PSL);
      uint4 ya = ld_relaxed4(ysrc), yb = ld_relaxed4(ysrc + NFFN * 4);
      const float rwin = __uint_as_float(((int)win.x < 0 ? win.x & 0x7fffffffu : ~win.x) & ~0x1ffu);
      const float rs = rbf(rcp(1.f + __expf(-rbf(rwin))));
      uint32_t n = 0;
      while (__any_sync(0xffffffffu, fh.y != tag || fx.y != tag)) { fh = ld_pair(fsrc); fx = ld_pair(fsrc + DM); watchdog(n); }
      while (!__all_sync(0xffffffffu, tag_ok(ya, tag) && tag_ok(yb, tag))) {
        if (!tag_ok(ya, tag)) ya = ld_relaxed4(ysrc);
        if (!tag_ok(yb, tag)) yb = ld_relaxed4(ysrc + NFFN * 4);
        watchdog(n);
      }
      __syncwarp();
      PROF(8, t3 == 0, 5);
      float y0 = untag_sum(ya.x, yb.x), y1 = untag_sum(ya.y, yb.y), y2 = untag_sum(ya.z, yb.z), y3 = untag_sum(ya.w, yb.w);
      const bool u1 = lane & 2, u2 = lane & 4;
      y0 = (u1 ? y2 : y0) + __shfl_xor_sync(0xffffffffu, u1 ? y0 : y2, 2);
      y1 = (u1 ? y3 : y1) + __shfl_xor_sync(0xffffffffu, u1 ? y1 : y3, 2);
      y0 = (u2 ? y1 : y0) + __shfl_xor_sync(0xffffffffu, u2 ? y0 : y1, 4);
      y0 += __shfl_xor_sync(0xffffffffu, y0, 8);
      if (!(lane & 8)) sts1(par + PAR_RED + 64 + (t3 >> 4) * 32 + ((lane & 1) * 4 + (lane & 2) + ((lane >> 2) & 1)) * 4, __float_as_uint(y0));
      bar_sync(4, 128);
      if (t3 < 4) {
        y0 = 0.f; y1 = 0.f;
#pragma unroll
        for (int w4 = 0; w4 < 7; w4++) {
          const uint2 v = lds2(par + PAR_RED + 64 + w4 * 32 + t3 * 8);
          y0 += __uint_as_float(v.x); y1 += __uint_as_float(v.y);
        }
        const uint2 gv = lds2(par + PAR_CONST + 16 + t3 * 8);
        const uint32_t upd = hmul2(pack_bf(y0, y1), pack_bf(rs, rs));
        *reinterpret_cast<uint32_t*>(P.out + (size_t)win.y * DM + b * 8 + t3 * 2) =
            hadd2(fx.x, hmul2(__byte_perm(gv.x, gv.y, 0x7632), hadd2(fh.x, upd)));
        if (b == 0 && t3 == 0) st_relaxed(&g_epoch, epoch + 1);
      }
      PROF(31, t3 == 0, 36);
    }
    cluster_wait();
  } else {
    const int wg = warp >> 2;

    uint32_t tag;
    {
      uint32_t* const pmod = g_modp + rank * 2 * DM + (b >> 1) * 32 + lane;
      uint32_t* const pln = g_ln1 + (rb * 128 + cj * 16 + warp) * 4;
      const uint32_t cv = ldg_nc1(P.c + rank * 512 + tid * 2);
      const uint32_t epoch = ld_relaxed(&g_epoch);
      if (warp == 0) st_relaxed(pmod, 0);
      if (lane == 0) { st_b128(pln, 0, 0, 0, 0); st_b128(pln + 32, 0, 0, 0, 0); }
      asm volatile("setmaxnreg.inc.sync.aligned.u32 232;");
      sts1(par + tid * 4, pack_bf(silu_f(bf_lo(cv)), silu_f(bf_hi(cv))));
      bar_sync(1, 320);
      tag = epoch % 3 + 1;
#pragma unroll
      for (int part = 0; part < 3; part++) {
        if (part != 1) {
          const uint32_t xa = base + (2 + part / 2) * GST_BYTES + warp * 2048 + lane * 16;
          mbar_wait(bar_hx + part * 4, 0);
          float s0 = 0.f, s1 = 0.f, q0 = 0.f, q1 = 0.f;
#pragma unroll
          for (int q = 0; q < 4; q++) {
            const uint4 xv = lds4(xa + q * 512);
            const uint32_t u[4] = {xv.x, xv.y, xv.z, xv.w};
#pragma unroll
            for (int e = 0; e < 4; e++) { const float lo = bf_lo(u[e]), hi = bf_hi(u[e]); s0 += lo; s1 += hi; q0 += lo * lo; q1 += hi * hi; }
          }
          s0 += s1; q0 += q1;
#pragma unroll
          for (int o = 16; o > 0; o >>= 1) { s0 += __shfl_xor_sync(0xffffffffu, s0, o); q0 += __shfl_xor_sync(0xffffffffu, q0, o); }
          const float mean = s0 * (1.f / DM);
          float mb, sd;
          ln_scalars(mean, fmaxf(q0 * (1.f / DM) - mean * mean, 0.f), mb, sd);
          uint32_t ih, il;
          split_inv(sd, ih, il);
          if (lane == 0) st_b128(pln + part * 16, pack_bf(mb, mb), ih, il, tag);
          PROF(1, tid == 0 && part == 2, 4);
        } else {
          const uint32_t fr = (lane & 7) + (lane >> 4) * 8, tq = lane & 3;
          const uint32_t wa = stage + warp * 4096 + fr * 64 + ((((lane >> 3) & 1) ^ ((fr >> 1) & 3)) << 4);
          uint32_t sc[8];
#pragma unroll
          for (int k = 0; k < 8; k++) sc[k] = lds1(par + warp * 128 + k * 16 + tq * 4);
          float d0[4] = {0.f, 0.f, 0.f, 0.f}, d1[4] = {0.f, 0.f, 0.f, 0.f};
          mbar_wait(bar_hw, 0);
#pragma unroll
          for (int ks = 0; ks < 4; ks++) {
            uint32_t w[8];
            ldmatrix4t(wa + ks * 1024, w[0], w[1], w[2], w[3]);
            ldmatrix4t((wa ^ 32) + ks * 1024, w[4], w[5], w[6], w[7]);
            mma16816(d0, w[0], w[1], w[2], w[3], sc[2 * ks], sc[2 * ks + 1]);
            mma16816(d1, w[4], w[5], w[6], w[7], sc[2 * ks], sc[2 * ks + 1]);
          }
          sts1(base + 2 * GST_BYTES + warp * 2048 + (tq * 8 + (lane >> 2)) * 4, __float_as_uint((tq & 2) ? ((tq & 1) ? d1[2] : d1[0]) : ((tq & 1) ? d0[2] : d0[0])));
          bar_sync(1, 256);
          if (warp == 0) {
            float s = 0.f;
#pragma unroll
            for (int w8 = 0; w8 < 8; w8++) s += __uint_as_float(lds1(base + 2 * GST_BYTES + w8 * 2048 + lane * 4));
            st_relaxed(pmod, (__float_as_uint(s) & ~3u) | tag);
          }
          PROF(1, tid == 0, 3);
        }
      }
      cluster_wait();
      if (wg == 1) bar_arrive(2, 256);
    }

    float f0 = 0.f, f1 = 0.f;
    const uint32_t rempty = lane < 2 ? mapa(bempty, lane & 1) : 0;
    constexpr uint32_t GE = NSLOT * 8 + 32;
    float o[64], s[64];
#pragma unroll 1
    for (int ps = 0; ps < 3; ps++) {
      {
        const uint32_t xt = ps == 1 ? XT1 : XT2, wt = ps == 1 ? WT1 : WT2;
        const int nst = ps == 2 ? 28 : 14;
        if (ps == 0) {
          float ga[64], gb[64];
#pragma unroll
          for (int i = 0; i < 64; i++) { ga[i] = 0.f; gb[i] = 0.f; }
          uint32_t a[2][16];
          const uint32_t l = fresh_lane();
          uint32_t fa[4];
#pragma unroll
          for (int kk = 0; kk < 4; kk++) fa[kk] = (base + wg * 8192 + frag_offset(warp)) ^ (kk * 32);
          const uint32_t mt = par + (l & 3) * 16;
          auto fetch = [&](int i, uint32_t (&f)[16], uint32_t z) {
            mbar_wait(xfull + (i & 3) * 8, i >> 2);
#pragma unroll
            for (int kk = 0; kk < 4; kk++) ldmatrix4(fa[kk] + (i & 3) * GST_BYTES + z, f[4 * kk], f[4 * kk + 1], f[4 * kk + 2], f[4 * kk + 3]);
          };
          uint4 r0, r1;
          {
            const uint32_t t7 = (warp & 3) * 32 + l;
            const uint32_t* pm = g_modp + wg * DM + ((cj * 128 + t7 * 4) & (DM - 1));
            const uint32_t* pr = g_ln1 + (rb * 128 + warp * 16 + (l >> 2)) * 4;
            uint4 m0 = ld_relaxed4(pm), m1 = ld_relaxed4(pm + 2 * DM);
            r0 = ld_b128(pr); r1 = ld_b128(pr + 32);
            fetch(0, a[0], 0); fetch(1, a[1], 0);
            uint32_t n = 0;
            bool written = false;
#pragma unroll 1
            while (true) {
              uint32_t miss;
              asm volatile("{ .reg .pred p0, p1, p2, p3; .reg .b32 t, u;\n"
                           "lop3.b32 t, %1, %2, %19, 0x7e; lop3.b32 u, %3, %4, %19, 0x7e; or.b32 t, t, u; and.b32 t, t, 3; setp.ne.u32 p0, t, 0;\n"
                           "lop3.b32 t, %5, %6, %19, 0x7e; lop3.b32 u, %7, %8, %19, 0x7e; or.b32 t, t, u; and.b32 t, t, 3; setp.ne.u32 p1, t, 0;\n"
                           "setp.ne.u32 p2, %12, %19; setp.ne.u32 p3, %16, %19;\n"
                           "@p0 ld.relaxed.gpu.global.v4.u32 {%1, %2, %3, %4}, [%17];\n"
                           "@p1 ld.relaxed.gpu.global.v4.u32 {%5, %6, %7, %8}, [%17 + 8192];\n"
                           "@p2 ld.relaxed.gpu.global.v4.u32 {%9, %10, %11, %12}, [%18];\n"
                           "@p3 ld.relaxed.gpu.global.v4.u32 {%13, %14, %15, %16}, [%18 + 128];\n"
                           "or.pred p0, p0, p1; or.pred p2, p2, p3; vote.sync.any.pred p0, p0, 0xffffffff; vote.sync.any.pred p2, p2, 0xffffffff;\n"
                           "selp.u32 t, 1, 0, p0; selp.u32 u, 2, 0, p2; or.b32 %0, t, u; }"
                           : "=r"(miss), "+r"(m0.x), "+r"(m0.y), "+r"(m0.z), "+r"(m0.w), "+r"(m1.x), "+r"(m1.y), "+r"(m1.z), "+r"(m1.w),
                             "+r"(r0.x), "+r"(r0.y), "+r"(r0.z), "+r"(r0.w), "+r"(r1.x), "+r"(r1.y), "+r"(r1.z), "+r"(r1.w)
                           : "l"(pm), "l"(pr), "r"(tag) : "memory");
              if (!(miss & 1) && !written) {
                written = true;
                float c0 = untag_sum(m0.x, m1.x), c1 = untag_sum(m0.y, m1.y), c2 = untag_sum(m0.z, m1.z), c3 = untag_sum(m0.w, m1.w);
                if (wg) { c0 = 1.f + rbf(c0); c1 = 1.f + rbf(c1); c2 = 1.f + rbf(c2); c3 = 1.f + rbf(c3); }
                const uint32_t d = par + (t7 >> 2) * 64 + (t7 & 1) * 32 + (t7 & 2) * 2 + (wg ? 0 : 8);
                sts1(d, pack_bf(c0, c1));
                sts1(d + 16, pack_bf(c2, c3));
                mbar_arrive(bar_mod);
              }
              if (!miss) break;
              watchdog(n);
            }
          }
          const uint32_t zero = r0.w ^ tag;
          auto normalize = [&](uint32_t (&f)[16]) {
#pragma unroll
            for (int k = 0; k < 16; k += 2) { f[k] = ln_norm(f[k], r0.x, r0.y, r0.z); f[k + 1] = ln_norm(f[k + 1], r1.x, r1.y, r1.z); }
          };
          auto modulate = [&](int i, uint32_t (&f)[16]) {
#pragma unroll
            for (int kk = 0; kk < 4; kk++) {
              const uint4 m = lds4(mt + i * 256 + kk * 64);
              f[4 * kk] = MODUL(f[4 * kk], m.x, m.z); f[4 * kk + 1] = MODUL(f[4 * kk + 1], m.x, m.z);
              f[4 * kk + 2] = MODUL(f[4 * kk + 2], m.y, m.w); f[4 * kk + 3] = MODUL(f[4 * kk + 3], m.y, m.w);
            }
            keep(f);
            mbar_arrive_pred(xempty + (i & 3) * 8, l == 0);
          };
          auto publish = [&](int u, uint32_t (&f)[16]) {
#pragma unroll
            for (int kk = 0; kk < 4; kk++) stmatrix4(fa[kk] + OFF_STAGE + u * UNIT, f[4 * kk], f[4 * kk + 1], f[4 * kk + 2], f[4 * kk + 3]);
            __syncwarp();
            mbar_arrive_pred(bar_hpub + u * 8, l == 0);
          };
          auto multiply = [&](int i, uint32_t (&f)[16]) {
            mbar_wait(gfull + (i & 3) * 8, i >> 2);
            const uint64_t db = make_desc(base + (i & 3) * GST_BYTES + UNIT, 8192, 1024);
            wg_fence();
#pragma unroll
            for (int kk = 0; kk < 4; kk++) mma256_rs(ga, gb, f[4 * kk], f[4 * kk + 1], f[4 * kk + 2], f[4 * kk + 3], db + kk * 128);
            wg_commit();
          };
          auto next = [&](int i, uint32_t (&f)[16]) {
            wg_wait<1>();
            mbar_arrive_cl(rempty, GE + ((i + 2) & 3) * 8);
            uint32_t z = zero;
#pragma unroll
            for (int k = 0; k < 16; k += 2) asm volatile("lop3.b32 %0, %1, %2, %0, 0xA8;" : "+r"(z) : "r"(f[k]), "r"(f[k + 1]));
            fetch(i, f, z);
            normalize(f); modulate(i, f); multiply(i, f);
          };
          normalize(a[0]); normalize(a[1]);
          keep(a[0]); keep(a[1]);
          mbar_wait(bar_mod, 0);
          PROF(1, tid == 0, 2);
          modulate(0, a[0]); multiply(0, a[0]); publish(0, a[0]);
          modulate(1, a[1]); multiply(1, a[1]); publish(1, a[1]);
#pragma unroll 1
          for (int i = 2; i < NRS; i += 2) { next(i, a[0]); next(i + 1, a[1]); }
          wg_wait<1>();
          mbar_arrive_cl(rempty, GE + ((NRS + 2) & 3) * 8);
#pragma unroll 1
          for (int i = NRS; i < 14; i++) {
            mbar_wait(xfull + (i & 3) * 8, (i >> 2) & 1);
            mbar_wait(gfull + (i & 3) * 8, (i >> 2) & 1);
            const uint32_t xa = base + (i & 3) * GST_BYTES;
            const uint64_t da = make_desc(xa + wg * 8192, 16, 1024), db = make_desc(xa + UNIT, 8192, 1024);
            if (i == 13) bar_sync(2 + wg, 256);
            wg_fence();
#pragma unroll
            for (int kk = 0; kk < 4; kk++) mma256_ss(ga, gb, da + kk * 2, db + kk * 128, 1);
            wg_commit();
            if (i == 13) bar_arrive(3 - wg, 256);
            wg_wait<1>();
            uint32_t z = zero;
#pragma unroll
            for (int k = 0; k < 16; k += 2) asm volatile("lop3.b32 %0, %1, %2, %0, 0xA8;" : "+r"(z) : "r"(a[1][k]), "r"(a[1][k + 1]));
            mbar_arrive_cl(rempty, GE + ((i + 3) & 3) * 8 + z);
            mbar_arrive_pred(xempty + ((i + 3) & 3) * 8, l == 0 && i != NRS);
          }
          mbar_wait(xfull + 16, 1);
          wg_wait<0>();
          keep(ga); keep(gb);
#pragma unroll
          for (int i = 0; i < 64; i++) {
            asm volatile("mov.b32 %0, %1;" : "=f"(s[i]) : "f"(ga[i]));
            asm volatile("mov.b32 %0, %1;" : "=f"(o[i]) : "f"(gb[i]));
          }
        } else {
          float ga[64], gb[64];
#pragma unroll
          for (int i = 0; i < 64; i++) {
            asm volatile("mov.b32 %0, %1;" : "=f"(ga[i]) : "f"(s[i]));
            asm volatile("mov.b32 %0, %1;" : "=f"(gb[i]) : "f"(o[i]));
          }
#pragma unroll 1
          for (int i = 0; i < nst; i++) {
            mbar_wait(gfull + (i & 3) * 8, (i >> 2) & 1);
            const uint64_t da = make_desc(base + unit_of(xt, i & 3) + wg * 8192, 16, 1024), db = make_desc(base + unit_of(wt, i & 3), 8192, 1024);
            if (i == nst - 1) bar_sync(2 + wg, 256);
            wg_fence();
#pragma unroll
            for (int kk = 0; kk < 4; kk++) mma256_ss(ga, gb, da + kk * 2, db + kk * 128, kk ? 1 : i);
            wg_commit();
            if (i == nst - 1) bar_arrive(3 - wg, 256);
            wg_wait<1>();
            mbar_arrive_cl(rempty, GE + ((i + 3) & 3) * 8, i != 0);
            PROF(4, tid == 0 && (i & 3) == 0, 40 + (ps - 1) * 4 + i / 4);
          }
          wg_wait<0>();
          keep(ga); keep(gb);
#pragma unroll
          for (int i = 0; i < 64; i++) {
            asm volatile("mov.b32 %0, %1;" : "=f"(s[i]) : "f"(ga[i]));
            asm volatile("mov.b32 %0, %1;" : "=f"(o[i]) : "f"(gb[i]));
          }
        }
        mbar_arrive_cl(rempty, GE + (ps == 2 ? 24 : 8));
        if (ps == 2) break;
      }
      const uint32_t qw = base + wg * 8192, qt = QT >> (16 * ps), at = ps ? AT1 : AT0;
      {
        const uint32_t wt = ps ? WT1 : WT0;
        const uint64_t da0 = make_desc(qw + unit_of(qt, 2), 16, 1024), da1 = make_desc(qw + unit_of(qt, 3), 16, 1024);
        const uint64_t db0 = make_desc(base + unit_of(wt, 2), 8192, 1024), db1 = make_desc(base + unit_of(wt, 3), 8192, 1024);
        mbar_wait(gfull + 16, 1);
        bar_sync(2 + wg, 256);
        wg_fence();
#pragma unroll
        for (int kk = 0; kk < 4; kk++) mma_ss<1>(s, da0 + kk * 2, db0 + kk * 128, 1);
        wg_commit();
        mbar_wait(xfull + 24, 1);
        mbar_wait(gfull + 24, 1);
        wg_fence();
#pragma unroll
        for (int kk = 0; kk < 4; kk++) mma_ss<1>(s, da1 + kk * 2, db1 + kk * 128, 1);
        wg_commit();
        bar_arrive(3 - wg, 256);
        mbar_wait(ps == 0 ? bar_pread : bar_ofree + 8, 0);
        wg_wait<0>();
        keep(s);
        PROF(2, tid == 0, 8 + ps * 8);
        store_chunk<0>(s, qw + unit_of(qt, 0) + frag_offset(warp));
        store_chunk<1>(s, qw + unit_of(qt, 1) + frag_offset(warp));
        fence_async_smem();
        bar_sync(2 + wg, 256);
        wg_fence();
#pragma unroll
        for (int kk = 0; kk < 8; kk++) mma_ss<1>(o, (kk < 4 ? da0 : da1) + (kk & 3) * 2, (kk < 4 ? db0 : db1) + UNIT / 16 + (kk & 3) * 128, 1);
        wg_commit();
        mbar_wait(bfull, 0);
        wg_fence();
        issue_qk(s, qw + unit_of(qt, 0), qw + unit_of(qt, 1), base + unit_of(at, 0));
        wg_commit();
        bar_arrive(3 - wg, 256);
        wg_wait<1>();
        keep(o);
        mbar_arrive_cl(rempty, GE + 16);
        mbar_arrive_cl(rempty, GE + 24);
        store_chunk<0>(o, qw + unit_of(qt, 2) + frag_offset(warp));
        store_chunk<1>(o, qw + unit_of(qt, 3) + frag_offset(warp));
        wg_wait<0>();
        keep(s);
        mbar_arrive_cl(rempty, 0);
      }
      PROF(4, tid == 0 && ps == 1, 61);
      float l0 = 0.f, l1 = 0.f;
      auto step = [&](auto odd_c, const int j, uint32_t (&pw)[32], uint32_t (&pr)[32]) {
        constexpr bool ODD = decltype(odd_c)::value;
        const bool first = !ODD && (j & 2) == 0, last = ODD && j == 7;
        const uint32_t ph = (j >> 1) & 1;
        float i0, i1, a0, a1;
        const bool so = !ODD && j == 4;
        if (so) { i0 = inv_quad_sum(l0); i1 = inv_quad_sum(l1); l0 = 0.f; l1 = 0.f; }
        bool redo = !ODD && (j | ps) == 0;
        while (true) {
          if (redo) {
            float m0 = fmaxf(s[0], s[1]), m1 = fmaxf(s[2], s[3]);
#pragma unroll
            for (int i = 1; i < 16; i++) { m0 = fmaxf(m0, fmaxf(s[4 * i], s[4 * i + 1])); m1 = fmaxf(m1, fmaxf(s[4 * i + 2], s[4 * i + 3])); }
            m0 = fmaxf(m0, __shfl_xor_sync(0xffffffffu, m0, 1)); m1 = fmaxf(m1, __shfl_xor_sync(0xffffffffu, m1, 1));
            m0 = fmaxf(m0, __shfl_xor_sync(0xffffffffu, m0, 2)); m1 = fmaxf(m1, __shfl_xor_sync(0xffffffffu, m1, 2));
            m0 *= SCL2; m1 *= SCL2;
            if (!first) {
              m0 = fmaxf(m0, f0); m1 = fmaxf(m1, f1);
              const float c0 = ex2(f0 - m0), c1 = ex2(f1 - m1);
              l0 *= c0; l1 *= c1;
              wg_wait<0>();
              keep(o);
#pragma unroll
              for (int i = 0; i < 16; i++) { o[4 * i] *= c0; o[4 * i + 1] *= c0; o[4 * i + 2] *= c1; o[4 * i + 3] *= c1; }
            }
            f0 = m0; f1 = m1;
          }
          float b0 = 0.f, b1 = 0.f;
          a0 = 0.f; a1 = 0.f;
#pragma unroll
          for (int i = 0; i < 16; i++) {
            const float e0 = ex2(fmaf(s[4 * i], SCL2, -f0)), e1 = ex2(fmaf(s[4 * i + 1], SCL2, -f0));
            const float e2 = ex2(fmaf(s[4 * i + 2], SCL2, -f1)), e3 = ex2(fmaf(s[4 * i + 3], SCL2, -f1));
            a0 += e0; b0 += e1; a1 += e2; b1 += e3;
            pw[2 * i] = pack_bf(e0, e1); pw[2 * i + 1] = pack_bf(e2, e3);
            if (i == VREL) {
#pragma unroll
              for (int k = 0; k < 2 * VREL + 2; k++) asm volatile("" : "+r"(pw[k])::"memory");
              mbar_wait(bar_mod, 0);
              wg_wait<0>();
              mbar_arrive_cl(rempty, ODD ? 16 : 0, !redo && (ODD || j));
#pragma unroll
              for (int k = 4 * VREL + 4; k < 64; k++) asm volatile("" : "+f"(s[k])::"memory");
            }
          }
          a0 += b0; a1 += b1;
          if (redo) break;
          redo = __any_sync(0xffffffffu, !(a0 + a1 < 0x1p90f));
          if (first) {
            uint32_t m0 = __ballot_sync(0xffffffffu, a0 > 0x1p-80f), m1 = __ballot_sync(0xffffffffu, a1 > 0x1p-80f);
            m0 |= m0 >> 1; m1 |= m1 >> 1; m0 |= m0 >> 2; m1 |= m1 >> 2;
            redo = redo || (m0 & m1 & 0x11111111u) != 0x11111111u;
          }
          if (!redo) break;
        }
        l0 += a0; l1 += a1;
        keep(pw);
        keep(o);
        if (so) store_chunk<0>(o, i0, i1, qw + unit_of(qt, 0) + frag_offset(warp));
        keep(o);
        if (ODD && !(j & 2)) { fence_async_smem(); mbar_arrive_pred(bar_ofull + wg * 8, j > 4); }
        mbar_wait(bfull + (ODD ? 24 : 8), ph);
        bar_sync(2 + wg, 256);
        if (!last) {
          const uint32_t qn = qt >> (j >= 3 ? 8 : 0);
          wg_fence();
          issue_qk(s, qw + unit_of(qn, 0), qw + unit_of(qn, 1), base + unit_of(at, ODD ? 3 : 1));
          wg_commit();
          mbar_wait(bfull + (ODD ? 0 : 16), ODD ? ph ^ 1 : ph);
        }
        if (so) { store_chunk<1>(o, i0, i1, qw + unit_of(qt, 1) + frag_offset(warp)); keep(o); }
        wg_fence();
        issue_pv(o, pw, base + unit_of(at, ODD ? (last ? 3 : 0) : 2), !first);
        wg_commit();
        bar_arrive(3 - wg, 256);
        wg_wait<1>();
        keep(s);
        mbar_arrive_cl(rempty, ODD ? 24 : 8, !last);
        PROF(4, tid == 0 && ps == 1, 51 + j);
      };
      uint32_t pa[32], pb[32];
#pragma unroll 1
      for (int j = 0; j < 8; j += 2) {
        step(std::false_type{}, j, pa, pb);
        step(std::true_type{}, j + 1, pb, pa);
      }
      {
        const float i0 = inv_quad_sum(l0), i1 = inv_quad_sum(l1);
        wg_wait<0>();
        keep(o);
        mbar_arrive_cl(rempty, 24);
        store_chunk<0>(o, i0, i1, qw + unit_of(qt, 2) + frag_offset(warp));
        store_chunk<1>(o, i0, i1, qw + unit_of(qt, 3) + frag_offset(warp));
        fence_async_smem();
        mbar_arrive(bar_ofull + 16 + wg * 8);
      }
      PROF(2, tid == 0, 10 + ps * 8);
    }

    const int ln = fresh_lane(), g = ln >> 2, tq = ln & 3, ct = warp * 32 + ln;
    const bool lane0 = ln == 0;
    const int lrow0 = warp * 16 + g;
    const int grow0 = rb * 128 + lrow0;
    const uint32_t res = base + OFF_RES, trow = res + wg * 8192 + frag_offset(warp);
    uint32_t xr[32];
    uint4 sv[4], own;
    uint32_t* sp[4];
#pragma unroll
    for (int k = 0; k < 4; k++) sp[k] = g_stats + ((((tq >> 1) * 4 + k) ^ cj) * SEQ + grow0 + (tq & 1) * 8) * 4;
    {
      const uint64_t da = make_desc(base + wg * 8192, 16, 1024), db = make_desc(base, 8192, 1024);
      constexpr int U = UNIT / 16;
#define HALF_STAGE(acc, xu, wu) _Pragma("unroll") for (int kk = 0; kk < 4; kk++) mma_ss<1>(acc, da + (xu) * U + kk * 2, db + (wu) * U + kk * 128, 1)
      PROF(10, ct == PT, 19); STAMP(0);
      cluster_arrive();
      mbar_wait(gfull, 1);
      mbar_wait(gfull + 8, 1);
      bar_sync(2 + wg, 256);
      wg_fence();
      HALF_STAGE(o, 7, 1);
      HALF_STAGE(o, 8, 3);
      wg_commit();
      STAMP(16);
      mbar_wait(gfull + 16, 1);
      STAMP(17);
      wg_fence();
      HALF_STAGE(o, 6, 11);
      wg_commit();
      bar_arrive(3 - wg, 256);
      mbar_wait(bar_par, 0);
      uint32_t* xo = g_xch + ((size_t)b * 8 * 256 + ct) * 4;
      const uint32_t* xi = g_xch + ((size_t)(b ^ 2) * 8 * 256 + ct) * 4;
      const uint32_t par1 = (~lds1(par + PAR_CONST + 4) & 1) << 16;
      uint32_t ga[16];
      uint4 bw[8];
#define LOAD_PAR _Pragma("unroll") for (int i = 0; i < 8; i++) {                                                               \
        if (!(i & 1)) {                                                                                                         \
          const uint4 t = lds4(par + PAR_SINK + i * 32 + tq * 16);                                                              \
          ga[2 * i] = t.x; ga[2 * i + 1] = t.y; ga[2 * i + 2] = t.z; ga[2 * i + 3] = t.w;                                       \
        }                                                                                                                       \
        bw[i] = lds4(par + PAR_T1 + i * 64 + tq * 16);                                                                          \
        if (!(g & 1)) { bw[i].x = 0x3f803f80u; bw[i].y = 0x3f803f80u; }                                                         \
      }
      if (PPOS == 0) LOAD_PAR
      wg_wait<1>();
      mbar_arrive_pred(bar_rel, lane0);
      wg_wait<0>();
      keep(o);
      mbar_arrive_pred(bar_ring, lane0);
      PROF(8, ct == PT, 20); STAMP(1);
#define SEND(i) st_b128(xo + (i) * 1024, (pack_bf(o[8 * (i)], o[8 * (i) + 1]) & ~0x10000u) | par1, pack_bf(o[8 * (i) + 2], o[8 * (i) + 3]), \
                        pack_bf(o[8 * (i) + 4], o[8 * (i) + 5]), pack_bf(o[8 * (i) + 6], o[8 * (i) + 7]))
#pragma unroll
      for (int i = 0; i < NS1; i++) SEND(i);
      PROF(8, ct == PT, 21); STAMP(2);
      bar_sync(2 + wg, 256);
      wg_fence();
      HALF_STAGE(s, 7, 0);
      HALF_STAGE(s, 8, 2);
      HALF_STAGE(s, 6, 10);
      wg_commit();
      bar_arrive(3 - wg, 256);
      STAMP(18);
      mbar_wait(gfull + 24, 1);
#pragma unroll
      for (int i = NS1; i < 8; i++) SEND(i);
      uint4 v[8];
#pragma unroll
      for (int i = 0; i < LD1; i++) v[i] = ld_b128(xi + i * 1024);
      if (PPOS == 1) LOAD_PAR
      STAMP(19);
      mbar_wait(bar_xres, 0);
      wg_wait<0>();
      mbar_arrive_pred(bar_ring + 8, lane0);
      bar_sync(2 + wg, 256);
      STAMP(20);
#pragma unroll
      for (int i = LD1; i < LD2; i++) v[i] = ld_b128(xi + i * 1024);
      mbar_wait(bar_xres, 0);
      wg_fence();
      HALF_STAGE(s, 9, 4);
      wg_commit();
      mbar_wait(bar_rx, 0);
      wg_fence();
      HALF_STAGE(s, 1, 5);
      wg_commit();
      bar_arrive(3 - wg, 256);
      STAMP(21);
#pragma unroll
      for (int i = LD2; i < 8; i++) v[i] = ld_b128(xi + i * 1024);
      if (LD2 < 8) mbar_wait(bar_xres, 0);
      if (PPOS >= 3) LOAD_PAR
      if (PPOS == 4) {
#pragma unroll
        for (int i = 0; i < 16; i += 2) ldmatrix4((trow ^ ((i & 7) << 4)) + (i >> 3) * 16384, xr[2 * i], xr[2 * i + 1], xr[2 * i + 2], xr[2 * i + 3]);
      }
      wg_wait<0>();
      keep(s);
      mbar_arrive_pred(bar_ring + 16, lane0);
      PROF(10, ct == PT, 23); STAMP(4);
      if (PPOS != 4) {
#pragma unroll
        for (int i = 0; i < 16; i += 2) ldmatrix4((trow ^ ((i & 7) << 4)) + (i >> 3) * 16384, xr[2 * i], xr[2 * i + 1], xr[2 * i + 2], xr[2 * i + 3]);
      }
      if (PPOS == 2) LOAD_PAR
      uint32_t pk[32];
      pack_p(s, pk);
      keep(pk);
      {
        uint32_t n = 0, miss;
        do {
          miss = 0;
#pragma unroll
          for (int i = 0; i < 8; i++) miss |= v[i].x ^ par1;
          miss = __any_sync(0xffffffffu, miss & 0x10000u);
          if (miss) {
#pragma unroll
            for (int i = 0; i < 8; i++)
              asm volatile("{ .reg .pred p; .reg .b32 t; xor.b32 t, %0, %5; and.b32 t, t, 0x10000; setp.ne.u32 p, t, 0;\n"
                           "@p ld.relaxed.gpu.global.v4.u32 {%0, %1, %2, %3}, [%4]; }"
                           : "+r"(v[i].x), "+r"(v[i].y), "+r"(v[i].z), "+r"(v[i].w) : "l"(xi + i * 1024), "r"(par1) : "memory");
          }
          watchdog(n);
        } while (miss);
      }
      PROF(8, ct == PT, 22); STAMP(3);
      float ds[4] = {0.f, 0.f, 0.f, 0.f}, dl[4] = {0.f, 0.f, 0.f, 0.f}, q0[4] = {0.f, 0.f, 0.f, 0.f}, q1[4] = {0.f, 0.f, 0.f, 0.f};
#pragma unroll
      for (int i = 0; i < 8; i++) {
        const uint32_t u0 = hfma2(ga[2 * i], hadd2(pk[4 * i], v[i].x & ~0x10000u), xr[4 * i]);
        const uint32_t u1 = hfma2(ga[2 * i], hadd2(pk[4 * i + 1], v[i].y), xr[4 * i + 1]);
        const uint32_t u2 = hfma2(ga[2 * i + 1], hadd2(pk[4 * i + 2], v[i].z), xr[4 * i + 2]);
        const uint32_t u3 = hfma2(ga[2 * i + 1], hadd2(pk[4 * i + 3], v[i].w), xr[4 * i + 3]);
        xr[4 * i] = u0; xr[4 * i + 1] = u1; xr[4 * i + 2] = u2; xr[4 * i + 3] = u3;
        mma16816(ds, u0, u1, u2, u3, bw[i].x, bw[i].y);
        mma16816(dl, u0, u1, u2, u3, bw[i].z, bw[i].w);
        mma16816(q0, u0, u1, u2, u3, u0, u2);
        mma16816(q1, u0, u1, u2, u3, u1, u3);
      }
      const float sqa = __shfl_sync(0xffffffffu, (g & 1) ? q0[1] : q0[0], g * 4 + (g >> 1));
      const float sqb = __shfl_sync(0xffffffffu, (g & 1) ? q1[3] : q1[2], g * 4 + (g >> 1));
      own = (tq & 1) ? make_uint4(__float_as_uint(ds[2]), __float_as_uint(sqb), __float_as_uint(ds[3] + dl[3]), tag)
                                 : make_uint4(__float_as_uint(ds[0]), __float_as_uint(sqa), __float_as_uint(ds[1] + dl[1]), tag);
      if (tq < 2) st_b128(sp[0], own.x, own.y, own.z, own.w);
#pragma unroll
      for (int k = 0; k < 4; k++) sv[k] = make_uint4(0, 0, 0, 0);
    }
    PROF(8, ct == PT, 29); STAMP(5);
    uint32_t mm, ih, il;
    float rbest;
    uint32_t wf[128];
    const uint32_t frow = (ln & 7) + (ln >> 4) * 8;
    const uint32_t wfo = base + (warp & 1) * 8192 + frow * 64 + ((((ln >> 3) & 1) ^ ((frow >> 1) & 3)) << 4);
#define LOAD_WF(m) _Pragma("unroll") for (int f = 0; f < 16; f++) {                                                   \
      const int r = ((f >> 1) * 4 + (m) * 2 + (f & 1)) * 4;                                                           \
      ldmatrix4t(((wfo + unit_of((m) ? FT_U : FT_G, warp >> 1)) ^ ((f & 1) * 32)) + (f >> 1) * 1024, wf[r], wf[r + 1], wf[r + 2], wf[r + 3]); \
    }
    bool early;
    {
#pragma unroll
      for (int i = 0; i < 16; i += 2) stmatrix4((trow ^ ((i & 7) << 4)) + (i >> 3) * 16384, xr[2 * i], xr[2 * i + 1], xr[2 * i + 2], xr[2 * i + 3]);
      const uint4 cst = lds4(par + PAR_CONST);
      const float A1 = __uint_as_float(cst.x), A2 = __uint_as_float(cst.z);
      uint32_t n = 0;
      early = false;
#pragma unroll 1
      while (true) {
        uint32_t miss;
        asm volatile("{ .reg .pred p0, p1, p2, p3; .reg .b64 u, v; .reg .b128 w;\n"
                     "setp.ge.u32 p0, %22, 2; setp.ne.and.u32 p0, %4, %21, p0; setp.ne.u32 p1, %8, %21; setp.ne.u32 p2, %12, %21; setp.ne.u32 p3, %16, %21;\n"
                     "@p0 ld.relaxed.gpu.global.v4.u32 {%1, %2, %3, %4}, [%17];\n"
                     "@p1 ld.relaxed.gpu.global.v4.u32 {%5, %6, %7, %8}, [%18];\n"
                     "@p2 ld.relaxed.gpu.global.v4.u32 {%9, %10, %11, %12}, [%19];\n"
                     "@p3 ld.relaxed.gpu.global.v4.u32 {%13, %14, %15, %16}, [%20];\n"
                     "or.pred p0, p0, p1; or.pred p2, p2, p3; or.pred p0, p0, p2; vote.sync.any.pred p0, p0, 0xffffffff; selp.u32 %0, 1, 0, p0; }"
                     : "=r"(miss), "+r"(sv[0].x), "+r"(sv[0].y), "+r"(sv[0].z), "+r"(sv[0].w), "+r"(sv[1].x), "+r"(sv[1].y), "+r"(sv[1].z), "+r"(sv[1].w),
                       "+r"(sv[2].x), "+r"(sv[2].y), "+r"(sv[2].z), "+r"(sv[2].w), "+r"(sv[3].x), "+r"(sv[3].y), "+r"(sv[3].z), "+r"(sv[3].w)
                     : "l"(sp[0]), "l"(sp[1]), "l"(sp[2]), "l"(sp[3]), "r"(tag), "r"(tq) : "memory");
        if (!miss) break;
        if (!early && (b >= NFFN || __all_sync(0xffffffffu, mbar_test(bar_box + (warp >> 1) * 8, 0)))) {
          early = true;
          LOAD_WF(0);
          __syncwarp();
          mbar_arrive_pred(bar_gate, lane0);
        }
        watchdog(n);
      }
      const uint4 v0 = tq < 2 ? own : sv[0], v1 = sv[1], v2 = sv[2], v3 = sv[3];
      PROF(8, ct == PT, 30); STAMP(6);
      float su = (__uint_as_float(v0.x) + __uint_as_float(v1.x)) + (__uint_as_float(v2.x) + __uint_as_float(v3.x));
      float sq = (__uint_as_float(v0.y) + __uint_as_float(v1.y)) + (__uint_as_float(v2.y) + __uint_as_float(v3.y));
      float dt = (__uint_as_float(v0.z) + __uint_as_float(v1.z)) + (__uint_as_float(v2.z) + __uint_as_float(v3.z));
      su += __shfl_xor_sync(0xffffffffu, su, 2); sq += __shfl_xor_sync(0xffffffffu, sq, 2); dt += __shfl_xor_sync(0xffffffffu, dt, 2);
      const float m = su * (1.f / DM);
      float mb, sd;
      ln_scalars(m, fmaxf(sq * (1.f / DM) - m * m, 0.f), mb, sd);
      const float inv = rcp(sd);
      rbest = (dt - mb * A1) * inv + A2;
      mm = pack_bf(mb, mb);
      ih = pack_bf(inv, inv);
      const float lo = inv - bf_lo(ih);
      il = pack_bf(lo, lo);
    }
    int ibest;
    {
      const uint32_t bits = __float_as_uint(rbest);
      const uint32_t key = (((int)bits < 0 ? ~bits : bits | 0x80000000u) & ~0x1ffu) | ((127 - lrow0 - (tq & 1) * 8) << 2) | tag;
      sts1(par + PAR_RED + warp * 4, __reduce_max_sync(0xffffffffu, key));
      PROF(8, ct == PT, 38); STAMP(7);
      bar_sync(1, 256);
      const uint4 ka = lds4(par + PAR_RED), kb = lds4(par + PAR_RED + 16);
      const uint32_t k2 = max(max(max(ka.x, ka.y), max(ka.z, ka.w)), max(max(kb.x, kb.y), max(kb.z, kb.w)));
      if (ct == 0 && cj == 0) st_relaxed(g_cand + rb, k2);
      ibest = 127 - ((k2 >> 2) & 127);
    }
    PROF(8, ct == PT, 39); STAMP(8);
    if ((ibest >> 4) == warp) {
      const int src = (ibest & 7) * 4 + ((ibest >> 3) & 1), ch = g * 2;
      const uint32_t cm = __shfl_sync(0xffffffffu, mm, src), ch_ = __shfl_sync(0xffffffffu, ih, src), cl = __shfl_sync(0xffffffffu, il, src);
      const uint32_t xa = res + (ch >> 3) * 16384 + ibest * 128 + (((ch & 7) ^ (ibest & 7)) << 4) + tq * 4;
      const uint32_t x0 = lds1(xa), x1 = lds1(xa ^ 16);
      const uint2 p0 = lds2(par + PAR_T2 + ch * 64 + tq * 16), p1 = lds2(par + PAR_T2 + ch * 64 + 64 + tq * 16);
      uint32_t* dst = g_row + rb * 2 * DM + cj * 128 + ln * 4;
      st_pairs(dst, ln_mod(x0, cm, ch_, cl, p0.x, p0.y), ln_mod(x1, cm, ch_, cl, p1.x, p1.y), tag);
      st_pairs(dst + DM, x0, x1, tag);
      __syncwarp();
    }
    PROF(8, ct == PT, 37); STAMP(9);
    uint32_t wd[64];
    const uint32_t wda = base + unit_of(FT_D, warp >> 1) + (warp & 1) * 8192 + frow * 128 + ((((ln >> 3) & 1) ^ (ln & 7)) << 4);
#define LOAD_WD(f) ldmatrix4t((wda ^ ((((f) >> 1) & 3) * 32)) + ((f) >> 3) * 4096 + ((f) & 1) * 2048, wd[4 * (f)], wd[4 * (f) + 1], wd[4 * (f) + 2], wd[4 * (f) + 3])
    if (!early) {
      if (b < NFFN) mbar_wait(bar_box + (warp >> 1) * 8, 0);
      LOAD_WF(0);
      __syncwarp();
      mbar_arrive_pred(bar_gate, lane0);
    }
    if (b < NFFN) {
      const uint32_t own = base + unit_of(FT_G, warp >> 1) + (warp & 1) * 8192;
      mbar_wait(bar_box + (4 + (warp >> 1)) * 8, 0);
      LOAD_WF(1);
      uint32_t* const ydst = g_ypart + ((size_t)(warp * 16 + tq * 2) * NFFN + b) * 8 + g;
      PROF(8, ct == PT, 31); STAMP(10);
      bool wdok;
      {
        uint32_t n = 0;
        while (!(wdok = __all_sync(0xffffffffu, mbar_test(bar_box + (8 + (warp >> 1)) * 8, 0))) && !__all_sync(0xffffffffu, mbar_test(bar_sel, 0))) watchdog(n);
      }
      if (wdok) {
#pragma unroll
        for (int f = 0; f < 16; f++) LOAD_WD(f);
      }
      STAMP(11);
      mbar_wait(bar_sel, 0);
      PROF(8, ct == PT, 33); STAMP(12);
      float d[8][4];
#pragma unroll
      for (int i = 0; i < 4; i++) { d[i][0] = 0.f; d[i][1] = 0.f; d[i][2] = 0.f; d[i][3] = 0.f; }
#pragma unroll
      for (int ks = 0; ks < 8; ks++) {
        const uint2 hb = lds2(own + 256 + ks * 32 + tq * 8);
#pragma unroll
        for (int mt = 0; mt < 4; mt++) {
          const int r = ks * 16 + mt * 4;
          mma16816(d[mt], wf[r], wf[r + 1], wf[r + 2], wf[r + 3], hb.x, hb.y);
        }
      }
      sts2(own + (tq * 8 + g) * 8, __float_as_uint((tq & 2) ? ((tq & 1) ? d[1][2] : d[1][0]) : ((tq & 1) ? d[0][2] : d[0][0])),
           __float_as_uint((tq & 2) ? ((tq & 1) ? d[3][2] : d[3][0]) : ((tq & 1) ? d[2][2] : d[2][0])));
      bar_sync(1, 256);
      uint32_t ab[4];
      {
        float G = 0.f, U = 0.f;
        uint2 pv[8];
#pragma unroll
        for (int w8 = 0; w8 < 8; w8++) pv[w8] = lds2(base + ln * 8 + ((FT_G >> (w8 >> 1) * 4) & 15) * UNIT + (w8 & 1) * 8192);
#pragma unroll
        for (int w8 = 0; w8 < 8; w8 += 2) {
          G += __uint_as_float(pv[w8].x) + __uint_as_float(pv[w8 + 1].x);
          U += __uint_as_float(pv[w8].y) + __uint_as_float(pv[w8 + 1].y);
        }
        const float act = rbf(silu_f(rbf(G))) * rbf(U);
        const uint32_t pk = pack_bf(act, __shfl_down_sync(0xffffffffu, act, 1));
#pragma unroll
        for (int i = 0; i < 4; i++) ab[i] = __shfl_sync(0xffffffffu, pk, i * 8 + tq * 2);
      }
      if (!wdok) {
        mbar_wait(bar_box + (8 + (warp >> 1)) * 8, 0);
#pragma unroll
        for (int f = 0; f < 16; f++) LOAD_WD(f);
      }
      PROF(8, ct == PT, 34); STAMP(13);
#pragma unroll
      for (int mt = 0; mt < 8; mt++) {
        d[mt][0] = 0.f; d[mt][1] = 0.f; d[mt][2] = 0.f; d[mt][3] = 0.f;
        mma16816(d[mt], wd[mt * 8], wd[mt * 8 + 1], wd[mt * 8 + 2], wd[mt * 8 + 3], ab[0], ab[1]);
        mma16816(d[mt], wd[mt * 8 + 4], wd[mt * 8 + 5], wd[mt * 8 + 6], wd[mt * 8 + 7], ab[2], ab[3]);
      }
#pragma unroll
      for (int i = 0; i < 4; i++) {
        const int m4 = (i >> 1) * 4, e = (i & 1) * 2;
        const float y = (tq & 2) ? ((tq & 1) ? d[m4 + 3][e] : d[m4 + 2][e]) : ((tq & 1) ? d[m4 + 1][e] : d[m4][e]);
        st_relaxed(ydst + (m4 * 2 + (i & 1)) * NFFN * 8, tagf(y, tag));
      }
      PROF(8, ct == PT, 35); STAMP(14);
    }
    mbar_wait(bar_sel, 0);
    mbar_arrive_pred(bar_win, ct == 0);
    const int iwin = lds1(par + PAR_CONST + 60) & 0x7ff;
    const bool cand = (iwin >> 4) == rb * 8 + warp;
    {
      const uint32_t mm0 = __shfl_sync(0xffffffffu, mm, ln & ~1), mm1 = __shfl_sync(0xffffffffu, mm, ln | 1);
      const uint32_t ih0 = __shfl_sync(0xffffffffu, ih, ln & ~1), ih1 = __shfl_sync(0xffffffffu, ih, ln | 1);
      const uint32_t il0 = __shfl_sync(0xffffffffu, il, ln & ~1), il1 = __shfl_sync(0xffffffffu, il, ln | 1);
#pragma unroll 1
      for (int hf = 0; hf < 2; hf++) {
        uint32_t x[16];
#pragma unroll
        for (int i = 0; i < 8; i += 2) ldmatrix4((trow ^ (i << 4)) + hf * 16384, x[2 * i], x[2 * i + 1], x[2 * i + 2], x[2 * i + 3]);
#pragma unroll
        for (int i = 0; i < 8; i++) {
          const uint4 pv = lds4(par + PAR_T2 + (hf * 8 + i) * 64 + tq * 16);
          x[2 * i] = hadd2(x[2 * i], hmul2(pv.z, ln_mod(x[2 * i], mm0, ih0, il0, pv.x, pv.y)));
          x[2 * i + 1] = hadd2(x[2 * i + 1], hmul2(pv.z, ln_mod(x[2 * i + 1], mm1, ih1, il1, pv.x, pv.y)));
        }
#pragma unroll
        for (int i = 0; i < 8; i += 2) stmatrix4((trow ^ (i << 4)) + hf * 16384, x[2 * i], x[2 * i + 1], x[2 * i + 2], x[2 * i + 3]);
      }
      if (!cand) fence_async_smem();
      __syncwarp();
      if (!cand && elect_one()) {
        tma2d_store(&maps.out, res + warp * 2048, cj * 128, rb * 128 + warp * 16);
        tma2d_store(&maps.out, res + 16384 + warp * 2048, cj * 128 + 64, rb * 128 + warp * 16);
        asm volatile("cp.async.bulk.commit_group;" ::: "memory");
      }
    }
    if (cand) {
      const int wrow0 = warp * 16;
#pragma unroll 2
      for (int p = 0; p < 8; p++) {
        const int row = 2 * p + (ln >> 4), ch = ln & 15;
        const uint4 v = lds4(res + (ch >> 3) * 16384 + (wrow0 + row) * 128 + (((ch & 7) ^ (row & 7)) << 4));
        if (rb * 128 + wrow0 + row != iwin) *reinterpret_cast<uint4*>(P.out + (size_t)(rb * 128 + wrow0 + row) * DM + cj * 128 + ch * 8) = v;
      }
    }
    asm volatile("cp.async.bulk.wait_group.read 0;" ::: "memory");
    PROF(8, ct == PT, 11); STAMP(15);
    cluster_wait();
  }
}

typedef CUresult (*EncodeFn)(CUtensorMap*, CUtensorMapDataType, cuuint32_t, void*, const cuuint64_t*, const cuuint64_t*,
                             const cuuint32_t*, const cuuint32_t*, CUtensorMapInterleave, CUtensorMapSwizzle,
                             CUtensorMapL2promotion, CUtensorMapFloatOOBfill);

void map2d(EncodeFn enc, CUtensorMap* m, const void* p, uint64_t rows, uint64_t cols, uint32_t brows) {
  cuuint64_t dims[2] = {cols, rows}, strides[1] = {cols * 2};
  cuuint32_t box[2] = {64, brows}, es[2] = {1, 1};
  enc(m, CU_TENSOR_MAP_DATA_TYPE_BFLOAT16, 2, const_cast<void*>(p), dims, strides, box, es, CU_TENSOR_MAP_INTERLEAVE_NONE,
      CU_TENSOR_MAP_SWIZZLE_128B, CU_TENSOR_MAP_L2_PROMOTION_L2_256B, CU_TENSOR_MAP_FLOAT_OOB_FILL_NONE);
}
void map2d_narrow(EncodeFn enc, CUtensorMap* m, const void* p, uint64_t rows, uint64_t cols, uint32_t brows) {
  cuuint64_t dims[2] = {cols, rows}, strides[1] = {cols * 2};
  cuuint32_t box[2] = {32, brows}, es[2] = {1, 1};
  enc(m, CU_TENSOR_MAP_DATA_TYPE_BFLOAT16, 2, const_cast<void*>(p), dims, strides, box, es, CU_TENSOR_MAP_INTERLEAVE_NONE,
      CU_TENSOR_MAP_SWIZZLE_64B, CU_TENSOR_MAP_L2_PROMOTION_L2_64B, CU_TENSOR_MAP_FLOAT_OOB_FILL_NONE);
}
void map3d(EncodeFn enc, CUtensorMap* m, const void* p, uint64_t rows, uint64_t cols, uint32_t brows, uint32_t nch) {
  cuuint64_t dims[3] = {64, rows, cols / 64}, strides[2] = {cols * 2, 128};
  cuuint32_t box[3] = {64, brows, nch}, es[3] = {1, 1, 1};
  enc(m, CU_TENSOR_MAP_DATA_TYPE_BFLOAT16, 3, const_cast<void*>(p), dims, strides, box, es, CU_TENSOR_MAP_INTERLEAVE_NONE,
      CU_TENSOR_MAP_SWIZZLE_128B, CU_TENSOR_MAP_L2_PROMOTION_L2_256B, CU_TENSOR_MAP_FLOAT_OOB_FILL_NONE);
}

}

extern "C" void kernel_launch(void* const* d_in, const int* in_sizes, int n_in, void* d_out, int out_size) {
  (void)in_sizes; (void)n_in; (void)out_size;
  static EncodeFn enc = nullptr;
  if (!enc) {
    void* fn = nullptr;
    cudaDriverEntryPointQueryResult st;
    cudaGetDriverEntryPoint("cuTensorMapEncodeTiled", &fn, cudaEnableDefault, &st);
    enc = (EncodeFn)fn;
    cudaFuncSetAttribute(fused_kernel, cudaFuncAttributeMaxDynamicSharedMemorySize, SMEM_BYTES);
  }
  Maps maps;
  map2d(enc, &maps.x, d_in[0], SEQ, DM, 128);
  map2d(enc, &maps.out, d_out, SEQ, DM, 16);
  map3d(enc, &maps.wq, d_in[3], DM, NQ, 64, 2);
  map3d(enc, &maps.k, d_in[1], 4 * SK, 128, 128, 1);
  map3d(enc, &maps.v, d_in[2], 4 * SK, 128, 128, 1);
  map3d(enc, &maps.wo, d_in[4], NQ, DM, 64, 2);
  map2d_narrow(enc, &maps.wg, d_in[7], DM, FF, 256);
  map2d_narrow(enc, &maps.wu, d_in[8], DM, FF, 256);
  map3d(enc, &maps.wd, d_in[9], FF, DM, 32, 4);
  map2d_narrow(enc, &maps.wm, d_in[11], DM, NMOD, 256);
  Ptrs p;
  p.x = (const __nv_bfloat16*)d_in[0];
  p.w_r = (const __nv_bfloat16*)d_in[6];
  p.w_gate = (const __nv_bfloat16*)d_in[7];
  p.w_up = (const __nv_bfloat16*)d_in[8];
  p.w_down = (const __nv_bfloat16*)d_in[9];
  p.c = (const __nv_bfloat16*)d_in[10];
  p.w_mod = (const __nv_bfloat16*)d_in[11];
  p.out = (__nv_bfloat16*)d_out;
  fused_kernel<<<NMAIN + NHELP, 384, SMEM_BYTES>>>(maps, p);
}
```

```cpp
#include <cuda_runtime.h>
#include <cuda_bf16.h>
#include <cuda.h>
#include <stdint.h>
#include <type_traits>

#define HD 2
#define HDX 2
#define NRS 8
#define FPACE 3
#define GOST 20
#define WB 2
#define WN 20
#define RES0 17
#define RES1 20
#define HU 32
#define NS1 5
#define PG0 15
#define PSL 0
#define FB0 0
#define FB2 8
#define OPS 8192
#define OFL 0
#define ODS 8
#define MODUL hfma2
#define ODS1 5
#define LD1 0
#define LD2 4
#define FB1 2
#define FPB 8
#define FPACE0 2
#define QRS 8
#define VREL 5
#define E0 3

namespace {

constexpr int SEQ = 2048, DM = 1024, NQ = 4096, SK = 2048, WIN = 512, FF = 3584, NMOD = 6144;
constexpr int NMAIN = 128, NHELP = 4, NFFN = 112;
constexpr int NSLOT = 4, SLOT_BYTES = 32768, UNIT = 16384, GST_BYTES = 3 * UNIT;
constexpr uint32_t XT1 = 0xDCBA, XT2 = 0x9687;
constexpr uint32_t WT0 = 0xA741, WT1 = 0x7420, WT2 = 0x4A20;
constexpr uint32_t AT0 = WT1, AT1 = WT2;
constexpr uint32_t QT = 0xDC9696DC;
constexpr int OFF_STAGE = 12 * UNIT;
constexpr uint32_t FT_G = 0x07B3, FT_U = 0xA628, FT_D = 0x5149;
constexpr int OFF_RES = 12 * UNIT;
constexpr int OFF_PAR = 14 * UNIT;
constexpr int OFF_BAR = OFF_PAR + 2528;
constexpr int SMEM_BYTES = OFF_BAR + 544;
static_assert(SMEM_BYTES <= 232448, "smem");

constexpr int PAR_T1 = 0;
constexpr int PAR_T2 = 512;
constexpr int PAR_CONST = 1536;
constexpr int PAR_RED = 1600;
constexpr int PAR_SINK = 2176;

struct Maps {
  CUtensorMap x, wq, k, v, wo, wg, wu, wd, wm, out;
};
struct Ptrs {
  const __nv_bfloat16 *x, *w_r, *c, *w_mod, *w_gate, *w_up, *w_down;
  __nv_bfloat16* out;
};

__device__ __align__(1024) uint8_t g_act[16 * 80 * UNIT];
__device__ __align__(128) uint32_t g_mod[NMOD];
__device__ __align__(128) uint32_t g_modp[2 * 2 * DM];
__device__ __align__(128) uint32_t g_ln1[SEQ * 4];
__device__ __align__(128) uint32_t g_cnt_h[16 * 32];
__device__ __align__(128) uint32_t g_cnt_o[128 * 32];
__device__ __align__(128) uint32_t g_xch[NMAIN * 8 * 256 * 4];
__device__ __align__(128) uint32_t g_stats[8 * SEQ * 4];
__device__ __align__(128) uint32_t g_cand[32];
__device__ __align__(128) uint32_t g_row[16 * 2 * DM];
__device__ __align__(128) uint32_t g_ypart[NMAIN * NFFN * 8];
__device__ uint32_t g_epoch;

__device__ __forceinline__ uint32_t fresh_lane() { uint32_t l; asm volatile("mov.u32 %0, %%laneid;" : "=r"(l)); return l; }
__device__ __forceinline__ uint32_t frag_offset(int warp) {
  const uint32_t l = fresh_lane();
  return ((warp & 3) * 16 + (l & 15)) * 128 + (((l >> 4) ^ (l & 7)) << 4);
}
__device__ __forceinline__ bool elect_one() {
  uint32_t p;
  asm volatile("{ .reg .pred q; elect.sync _|q, 0xffffffff; selp.u32 %0, 1, 0, q; }" : "=r"(p));
  return p;
}
__device__ __forceinline__ uint32_t smem_u32(const void* p) { return (uint32_t)__cvta_generic_to_shared(p); }
__device__ __forceinline__ void mbar_init(uint32_t bar, uint32_t cnt) {
  asm volatile("mbarrier.init.shared::cta.b64 [%0], %1;" ::"r"(bar), "r"(cnt) : "memory");
}
__device__ __forceinline__ void mbar_expect_tx(uint32_t bar, uint32_t bytes) {
  asm volatile("mbarrier.arrive.expect_tx.shared::cta.b64 _, [%0], %1;" ::"r"(bar), "r"(bytes) : "memory");
}
__device__ __forceinline__ void mbar_arrive(uint32_t bar) {
  asm volatile("mbarrier.arrive.shared::cta.b64 _, [%0];" ::"r"(bar) : "memory");
}
__device__ __forceinline__ void mbar_arrive_pred(uint32_t bar, bool p) {
  asm volatile("{ .reg .pred p; setp.ne.b32 p, %1, 0; @p mbarrier.arrive.shared::cta.b64 _, [%0]; }" ::"r"(bar), "r"((int)p) : "memory");
}
__device__ __forceinline__ void mbar_arrive_cl(uint32_t bar, uint32_t off, bool p = true) {
  asm volatile("{ .reg .pred p, q; .reg .b32 a; setp.ne.b32 q, %2, 0; setp.ne.and.b32 p, %0, 0, q; add.u32 a, %0, %1; @p mbarrier.arrive.shared::cluster.b64 _, [a]; }"
               ::"r"(bar), "r"(off), "r"((int)p) : "memory");
}
__device__ __forceinline__ uint32_t mapa(uint32_t addr, uint32_t cta) {
  uint32_t r; asm("mapa.shared::cluster.u32 %0, %1, %2;" : "=r"(r) : "r"(addr), "r"(cta)); return r;
}
__device__ __forceinline__ void cluster_arrive() { asm volatile("barrier.cluster.arrive.relaxed.aligned;" ::: "memory"); }
__device__ __forceinline__ void cluster_wait() { asm volatile("barrier.cluster.wait.aligned;" ::: "memory"); }
__device__ __forceinline__ void watchdog(uint32_t& n) {
}
__device__ __forceinline__ void mbar_wait(uint32_t bar, uint32_t parity) {
  asm volatile("{\n.reg .pred p;\nWAIT_%=:\nmbarrier.try_wait.parity.shared::cta.b64 p, [%0], %1;\n@!p bra WAIT_%=;\n}" ::"r"(bar), "r"(parity) : "memory");
}
__device__ __forceinline__ bool mbar_test(uint32_t bar, uint32_t parity) {
  uint32_t ok;
  asm volatile("{\n.reg .pred p;\nmbarrier.test_wait.parity.shared::cta.b64 p, [%1], %2;\nselp.u32 %0, 1, 0, p;\n}" : "=r"(ok) : "r"(bar), "r"(parity) : "memory");
  return ok;
}
__device__ __forceinline__ uint64_t l2_stream() {
  uint64_t f; asm("createpolicy.fractional.L2::evict_first.b64 %0, 1.0;" : "=l"(f)); return f;
}
__device__ __forceinline__ void tma2d(uint32_t dst, const CUtensorMap* m, int c0, int c1, uint32_t bar) {
  asm volatile("cp.async.bulk.tensor.2d.shared::cluster.global.mbarrier::complete_tx::bytes.L2::cache_hint [%0], [%1, {%3, %4}], [%2], %5;"
               ::"r"(dst), "l"(m), "r"(bar), "r"(c0), "r"(c1), "l"(l2_stream()) : "memory");
}
__device__ __forceinline__ void bulk_load(uint32_t dst, const void* src, uint32_t bytes, uint32_t bar) {
  asm volatile("cp.async.bulk.shared::cluster.global.mbarrier::complete_tx::bytes [%0], [%1], %2, [%3];" ::"r"(dst), "l"(src), "r"(bytes), "r"(bar) : "memory");
}
__device__ __forceinline__ void bulk_load_stream(uint32_t dst, const void* src, uint32_t bytes, uint32_t bar) {
  asm volatile("cp.async.bulk.shared::cluster.global.mbarrier::complete_tx::bytes.L2::cache_hint [%0], [%1], %2, [%3], %4;"
               ::"r"(dst), "l"(src), "r"(bytes), "r"(bar), "l"(l2_stream()) : "memory");
}
__device__ __forceinline__ void tma2d_store(const CUtensorMap* m, uint32_t src, int c0, int c1) {
  asm volatile("cp.async.bulk.tensor.2d.global.shared::cta.bulk_group [%0, {%2, %3}], [%1];" ::"l"(m), "r"(src), "r"(c0), "r"(c1) : "memory");
}
__device__ __forceinline__ void bulk_store(void* dst, uint32_t src, uint32_t bytes) {
  asm volatile("cp.async.bulk.global.shared::cta.bulk_group [%0], [%1], %2;" ::"l"(dst), "r"(src), "r"(bytes) : "memory");
}
__device__ __forceinline__ uint32_t unit_of(uint32_t table, uint32_t i) { return ((table >> (i * 4)) & 15) * UNIT; }
__device__ __forceinline__ void tma3d(uint32_t dst, const CUtensorMap* m, int c0, int c1, int c2, uint32_t bar) {
  asm volatile("cp.async.bulk.tensor.3d.shared::cluster.global.mbarrier::complete_tx::bytes.L2::cache_hint [%0], [%1, {%3, %4, %5}], [%2], %6;"
               ::"r"(dst), "l"(m), "r"(bar), "r"(c0), "r"(c1), "r"(c2), "l"(l2_stream()) : "memory");
}
template <bool STREAM>
__device__ __forceinline__ void tma3d_mc(uint32_t dst, const CUtensorMap* m, int c0, int c1, int c2, uint32_t bar) {
  if (STREAM)
    asm volatile("cp.async.bulk.tensor.3d.shared::cluster.global.mbarrier::complete_tx::bytes.multicast::cluster.L2::cache_hint [%0], [%1, {%3, %4, %5}], [%2], %6, %7;"
                 ::"r"(dst), "l"(m), "r"(bar), "r"(c0), "r"(c1), "r"(c2), "h"((uint16_t)3), "l"(l2_stream()) : "memory");
  else
    asm volatile("cp.async.bulk.tensor.3d.shared::cluster.global.mbarrier::complete_tx::bytes.multicast::cluster [%0], [%1, {%3, %4, %5}], [%2], %6;"
                 ::"r"(dst), "l"(m), "r"(bar), "r"(c0), "r"(c1), "r"(c2), "h"((uint16_t)3) : "memory");
}
__device__ __forceinline__ void prefetch_map(const CUtensorMap* m) {
  asm volatile("prefetch.tensormap [%0];" ::"l"(m) : "memory");
}
__device__ __forceinline__ void fence_async() { asm volatile("fence.proxy.async.global;" ::: "memory"); }
__device__ __forceinline__ void fence_async_smem() { asm volatile("fence.proxy.async.shared::cta;" ::: "memory"); }
__device__ __forceinline__ void bar_sync(int id, int n) { asm volatile("bar.sync %0, %1;" ::"r"(id), "r"(n) : "memory"); }
__device__ __forceinline__ void bar_arrive(int id, int n) { asm volatile("bar.arrive %0, %1;" ::"r"(id), "r"(n) : "memory"); }
__device__ __forceinline__ void wg_fence() { asm volatile("wgmma.fence.sync.aligned;" ::: "memory"); }
__device__ __forceinline__ void wg_commit() { asm volatile("wgmma.commit_group.sync.aligned;" ::: "memory"); }
template <int N> __device__ __forceinline__ void wg_wait() { asm volatile("wgmma.wait_group.sync.aligned %0;" ::"n"(N) : "memory"); }
__device__ __forceinline__ uint64_t make_desc(uint32_t addr, uint32_t lbo, uint32_t sbo) {
  return (uint64_t)((addr & 0x3FFFF) >> 4) | ((uint64_t)(lbo >> 4) << 16) | ((uint64_t)(sbo >> 4) << 32) | (1ull << 62);
}
__device__ __forceinline__ uint32_t ld_relaxed(const uint32_t* p) {
  uint32_t v; asm volatile("ld.relaxed.gpu.global.u32 %0, [%1];" : "=r"(v) : "l"(p) : "memory"); return v;
}
__device__ __forceinline__ uint32_t ld_acquire(const uint32_t* p) {
  uint32_t v; asm volatile("ld.acquire.gpu.global.u32 %0, [%1];" : "=r"(v) : "l"(p) : "memory"); return v;
}
__device__ __forceinline__ uint4 ld_relaxed4(const uint32_t* p) {
  uint4 v; asm volatile("ld.relaxed.gpu.global.v4.u32 {%0,%1,%2,%3}, [%4];" : "=r"(v.x), "=r"(v.y), "=r"(v.z), "=r"(v.w) : "l"(p) : "memory"); return v;
}
__device__ __forceinline__ uint2 ld_relaxed2(const uint32_t* p) {
  uint2 v; asm volatile("ld.relaxed.gpu.global.v2.u32 {%0,%1}, [%2];" : "=r"(v.x), "=r"(v.y) : "l"(p) : "memory"); return v;
}
__device__ __forceinline__ void st_relaxed(uint32_t* p, uint32_t v) {
  asm volatile("st.relaxed.gpu.global.u32 [%0], %1;" ::"l"(p), "r"(v) : "memory");
}
__device__ __forceinline__ void st_relaxed2(uint32_t* p, uint32_t a, uint32_t b) {
  asm volatile("st.relaxed.gpu.global.v2.u32 [%0], {%1,%2};" ::"l"(p), "r"(a), "r"(b) : "memory");
}
__device__ __forceinline__ void st_relaxed4(uint32_t* p, uint32_t a, uint32_t b, uint32_t c, uint32_t d) {
  asm volatile("st.relaxed.gpu.global.v4.u32 [%0], {%1,%2,%3,%4};" ::"l"(p), "r"(a), "r"(b), "r"(c), "r"(d) : "memory");
}
__device__ __forceinline__ void st_b128(uint32_t* p, uint32_t a, uint32_t b, uint32_t c, uint32_t d) {
  asm volatile("{ .reg .b64 u, v; .reg .b128 w; mov.b64 u, {%1, %2}; mov.b64 v, {%3, %4}; mov.b128 w, {u, v}; st.relaxed.gpu.global.b128 [%0], w; }"
               ::"l"(p), "r"(a), "r"(b), "r"(c), "r"(d) : "memory");
}
__device__ __forceinline__ uint4 ld_b128(const uint32_t* p) {
  uint4 r;
  asm volatile("{ .reg .b64 u, v; .reg .b128 w; ld.relaxed.gpu.global.b128 w, [%4]; mov.b128 {u, v}, w; mov.b64 {%0, %1}, u; mov.b64 {%2, %3}, v; }"
               : "=r"(r.x), "=r"(r.y), "=r"(r.z), "=r"(r.w) : "l"(p) : "memory");
  return r;
}
__device__ __forceinline__ void st_pairs(uint32_t* p, uint32_t a, uint32_t b, uint32_t tag) {
  asm volatile("{ .reg .b64 u, v; mov.b64 u, {%1, %3}; mov.b64 v, {%2, %3}; st.relaxed.gpu.global.v2.b64 [%0], {u, v}; }"
               ::"l"(p), "r"(a), "r"(b), "r"(tag) : "memory");
}
__device__ __forceinline__ uint4 ld_pairs(const uint32_t* p) {
  uint4 v;
  asm volatile("{ .reg .b64 u, v; ld.relaxed.gpu.global.v2.b64 {u, v}, [%4]; mov.b64 {%0, %1}, u; mov.b64 {%2, %3}, v; }"
               : "=r"(v.x), "=r"(v.y), "=r"(v.z), "=r"(v.w) : "l"(p) : "memory");
  return v;
}
__device__ __forceinline__ uint2 ld_pair(const uint32_t* p) {
  uint2 v;
  asm volatile("{ .reg .b64 u; ld.relaxed.gpu.global.b64 u, [%2]; mov.b64 {%0, %1}, u; }" : "=r"(v.x), "=r"(v.y) : "l"(p) : "memory");
  return v;
}
__device__ __forceinline__ void red_release(uint32_t* p, uint32_t v) {
  asm volatile("red.release.gpu.global.add.u32 [%0], %1;" ::"l"(p), "r"(v) : "memory");
}
__device__ __forceinline__ uint32_t ldg_nc1(const void* p) {
  uint32_t v;
  asm volatile("ld.global.nc.u32 %0, [%1];" : "=r"(v) : "l"(p));
  return v;
}
__device__ __forceinline__ uint4 ldg_nc4(const void* p) {
  uint4 v; asm volatile("ld.global.nc.L1::no_allocate.v4.u32 {%0,%1,%2,%3}, [%4];" : "=r"(v.x), "=r"(v.y), "=r"(v.z), "=r"(v.w) : "l"(p)); return v;
}
__device__ __forceinline__ uint4 ldg_stream4(const void* p) {
  uint4 v;
  asm volatile("ld.global.nc.L1::no_allocate.L2::cache_hint.v4.u32 {%0,%1,%2,%3}, [%4], %5;" : "=r"(v.x), "=r"(v.y), "=r"(v.z), "=r"(v.w) : "l"(p), "l"(l2_stream()));
  return v;
}
__device__ __forceinline__ void stg4(void* p, uint4 v) {
  asm volatile("st.global.v4.u32 [%0], {%1,%2,%3,%4};" ::"l"(p), "r"(v.x), "r"(v.y), "r"(v.z), "r"(v.w) : "memory");
}
__device__ __forceinline__ void wait_counter(const uint32_t* p, uint32_t target) {
  uint32_t n = 0;
  while (__any_sync(0xffffffffu, (int)(ld_acquire(p) - target) < 0)) { watchdog(n); }
}
__device__ __forceinline__ uint32_t tagf(float v, uint32_t tag) { return (__float_as_uint(v) & ~3u) | tag; }
__device__ __forceinline__ bool tag_ok(uint4 v, uint32_t tag) { return (((v.x ^ tag) | (v.y ^ tag) | (v.z ^ tag) | (v.w ^ tag)) & 3u) == 0; }
__device__ __forceinline__ float untag_sum(uint32_t a, uint32_t b) { return __uint_as_float(a & ~3u) + __uint_as_float(b & ~3u); }
__device__ __forceinline__ uint4 poll4(const uint32_t* p, uint32_t tag) {
  uint4 v = ld_relaxed4(p);
  uint32_t n = 0;
  while (!__all_sync(0xffffffffu, tag_ok(v, tag))) { v = ld_relaxed4(p); watchdog(n); }
  return v;
}
__device__ __forceinline__ float bf_lo(uint32_t v) { return __uint_as_float(v << 16); }
__device__ __forceinline__ float bf_hi(uint32_t v) { return __uint_as_float(v & 0xffff0000u); }
__device__ __forceinline__ uint32_t pack_bf(float lo, float hi) {
  uint32_t r; asm("cvt.rn.bf16x2.f32 %0, %1, %2;" : "=r"(r) : "f"(hi), "f"(lo)); return r;
}
__device__ __forceinline__ float rbf(float v) { return __uint_as_float(pack_bf(0.f, v) & 0xffff0000u); }
__device__ __forceinline__ uint32_t hmul2(uint32_t a, uint32_t b) {
  uint32_t r; asm("mul.rn.bf16x2 %0, %1, %2;" : "=r"(r) : "r"(a), "r"(b)); return r;
}
__device__ __forceinline__ uint32_t hadd2(uint32_t a, uint32_t b) {
  uint32_t r; asm("add.rn.bf16x2 %0, %1, %2;" : "=r"(r) : "r"(a), "r"(b)); return r;
}
__device__ __forceinline__ uint32_t hsub2(uint32_t a, uint32_t b) {
  uint32_t r; asm("sub.rn.bf16x2 %0, %1, %2;" : "=r"(r) : "r"(a), "r"(b)); return r;
}
__device__ __forceinline__ uint32_t hmax2(uint32_t a, uint32_t b) {
  uint32_t r; asm("max.bf16x2 %0, %1, %2;" : "=r"(r) : "r"(a), "r"(b)); return r;
}
__device__ __forceinline__ float rcp(float x) { float r; asm("rcp.approx.ftz.f32 %0, %1;" : "=f"(r) : "f"(x)); return r; }
__device__ __forceinline__ float ex2(float x) { float r; asm("ex2.approx.ftz.f32 %0, %1;" : "=f"(r) : "f"(x)); return r; }
__device__ __forceinline__ void stmatrix4(uint32_t addr, uint32_t a, uint32_t b, uint32_t c, uint32_t d) {
  asm volatile("stmatrix.sync.aligned.m8n8.x4.shared.b16 [%0], {%1,%2,%3,%4};" ::"r"(addr), "r"(a), "r"(b), "r"(c), "r"(d) : "memory");
}
__device__ __forceinline__ void ldmatrix4(uint32_t addr, uint32_t& a, uint32_t& b, uint32_t& c, uint32_t& d) {
  asm volatile("ldmatrix.sync.aligned.m8n8.x4.shared.b16 {%0,%1,%2,%3}, [%4];" : "=r"(a), "=r"(b), "=r"(c), "=r"(d) : "r"(addr) : "memory");
}
__device__ __forceinline__ void ldmatrix4t(uint32_t addr, uint32_t& a, uint32_t& b, uint32_t& c, uint32_t& d) {
  asm volatile("ldmatrix.sync.aligned.m8n8.x4.trans.shared.b16 {%0,%1,%2,%3}, [%4];" : "=r"(a), "=r"(b), "=r"(c), "=r"(d) : "r"(addr) : "memory");
}
__device__ __forceinline__ void mma16816(float (&d)[4], uint32_t a0, uint32_t a1, uint32_t a2, uint32_t a3, uint32_t b0, uint32_t b1) {
  asm volatile("mma.sync.aligned.m16n8k16.row.col.f32.bf16.bf16.f32 {%0,%1,%2,%3}, {%4,%5,%6,%7}, {%8,%9}, {%0,%1,%2,%3};"
               : "+f"(d[0]), "+f"(d[1]), "+f"(d[2]), "+f"(d[3]) : "r"(a0), "r"(a1), "r"(a2), "r"(a3), "r"(b0), "r"(b1));
}
__device__ __forceinline__ void sts1(uint32_t a, uint32_t v) { asm volatile("st.shared.u32 [%0], %1;" ::"r"(a), "r"(v) : "memory"); }
__device__ __forceinline__ uint4 lds4(uint32_t a) {
  uint4 v; asm volatile("ld.shared.v4.u32 {%0,%1,%2,%3}, [%4];" : "=r"(v.x), "=r"(v.y), "=r"(v.z), "=r"(v.w) : "r"(a) : "memory"); return v;
}
__device__ __forceinline__ uint2 lds2(uint32_t a) {
  uint2 v; asm volatile("ld.shared.v2.u32 {%0,%1}, [%2];" : "=r"(v.x), "=r"(v.y) : "r"(a) : "memory"); return v;
}
__device__ __forceinline__ uint32_t lds1(uint32_t a) {
  uint32_t v; asm volatile("ld.shared.u32 %0, [%1];" : "=r"(v) : "r"(a) : "memory"); return v;
}
__device__ __forceinline__ void sts2(uint32_t a, uint32_t x, uint32_t y) { asm volatile("st.shared.v2.u32 [%0], {%1,%2};" ::"r"(a), "r"(x), "r"(y) : "memory"); }
__device__ __forceinline__ void sts4(uint32_t a, uint4 v) {
  asm volatile("st.shared.v4.u32 [%0], {%1,%2,%3,%4};" ::"r"(a), "r"(v.x), "r"(v.y), "r"(v.z), "r"(v.w) : "memory");
}
__device__ __forceinline__ float silu_f(float v) { return __fdividef(v, 1.f + __expf(-v)); }
__device__ __forceinline__ uint32_t hfma2(uint32_t a, uint32_t b, uint32_t c) {
  uint32_t r; asm("fma.rn.bf16x2 %0, %1, %2, %3;" : "=r"(r) : "r"(a), "r"(b), "r"(c)); return r;
}
__device__ __forceinline__ void split_inv(float sd, uint32_t& ih, uint32_t& il) {
  const float inv = rcp(sd);
  ih = pack_bf(inv, inv);
  const float lo = inv - bf_lo(ih);
  il = pack_bf(lo, lo);
}
__device__ __forceinline__ uint32_t ln_norm(uint32_t x, uint32_t mean2, uint32_t ih, uint32_t il) {
  const uint32_t d = hsub2(x, mean2);
  return hfma2(d, ih, hmul2(d, il));
}
__device__ __forceinline__ uint32_t modul(uint32_t n, uint32_t c1, uint32_t sh) { return hadd2(hmul2(n, c1), sh); }
__device__ __forceinline__ uint32_t ln_mod(uint32_t x, uint32_t mean2, uint32_t ih, uint32_t il, uint32_t c1, uint32_t sh) {
  return modul(ln_norm(x, mean2, ih, il), c1, sh);
}

#define R8(a, i) "+f"(a[i]), "+f"(a[i + 1]), "+f"(a[i + 2]), "+f"(a[i + 3]), "+f"(a[i + 4]), "+f"(a[i + 5]), "+f"(a[i + 6]), "+f"(a[i + 7])
#define D64 "{%0,%1,%2,%3,%4,%5,%6,%7,%8,%9,%10,%11,%12,%13,%14,%15,%16,%17,%18,%19,%20,%21,%22,%23,%24,%25,%26,%27,%28,%29,%30,%31," \
            "%32,%33,%34,%35,%36,%37,%38,%39,%40,%41,%42,%43,%44,%45,%46,%47,%48,%49,%50,%51,%52,%53,%54,%55,%56,%57,%58,%59,%60,%61,%62,%63}"
template <int TB>
__device__ __forceinline__ void mma_ss(float (&d)[64], uint64_t da, uint64_t db, int sc) {
  asm volatile("{\n.reg .pred p;\nsetp.ne.b32 p, %66, 0;\n"
               "wgmma.mma_async.sync.aligned.m64n128k16.f32.bf16.bf16 " D64 ", %64, %65, p, 1, 1, 0, %67;\n}"
               : R8(d, 0), R8(d, 8), R8(d, 16), R8(d, 24), R8(d, 32), R8(d, 40), R8(d, 48), R8(d, 56)
               : "l"(da), "l"(db), "r"(sc), "n"(TB));
}
template <int TB>
__device__ __forceinline__ void mma_rs(float (&d)[64], uint32_t a0, uint32_t a1, uint32_t a2, uint32_t a3, uint64_t db, int sc) {
  asm volatile("{\n.reg .pred p;\nsetp.ne.b32 p, %69, 0;\n"
               "wgmma.mma_async.sync.aligned.m64n128k16.f32.bf16.bf16 " D64 ", {%64,%65,%66,%67}, %68, p, 1, 1, %70;\n}"
               : R8(d, 0), R8(d, 8), R8(d, 16), R8(d, 24), R8(d, 32), R8(d, 40), R8(d, 48), R8(d, 56)
               : "r"(a0), "r"(a1), "r"(a2), "r"(a3), "l"(db), "r"(sc), "n"(TB));
}
#define D128 "{%0,%1,%2,%3,%4,%5,%6,%7,%8,%9,%10,%11,%12,%13,%14,%15,%16,%17,%18,%19,%20,%21,%22,%23,%24,%25,%26,%27,%28,%29,%30,%31," \
             "%32,%33,%34,%35,%36,%37,%38,%39,%40,%41,%42,%43,%44,%45,%46,%47,%48,%49,%50,%51,%52,%53,%54,%55,%56,%57,%58,%59,%60,%61,%62,%63," \
             "%64,%65,%66,%67,%68,%69,%70,%71,%72,%73,%74,%75,%76,%77,%78,%79,%80,%81,%82,%83,%84,%85,%86,%87,%88,%89,%90,%91,%92,%93,%94,%95," \
             "%96,%97,%98,%99,%100,%101,%102,%103,%104,%105,%106,%107,%108,%109,%110,%111,%112,%113,%114,%115,%116,%117,%118,%119,%120,%121,%122,%123,%124,%125,%126,%127}"
#define R128(d, e) R8(d, 0), R8(d, 8), R8(d, 16), R8(d, 24), R8(d, 32), R8(d, 40), R8(d, 48), R8(d, 56), \
                   R8(e, 0), R8(e, 8), R8(e, 16), R8(e, 24), R8(e, 32), R8(e, 40), R8(e, 48), R8(e, 56)
__device__ __forceinline__ void mma256_ss(float (&d)[64], float (&e)[64], uint64_t da, uint64_t db, int sc) {
  asm volatile("{\n.reg .pred p;\nsetp.ne.b32 p, %130, 0;\n"
               "wgmma.mma_async.sync.aligned.m64n256k16.f32.bf16.bf16 " D128 ", %128, %129, p, 1, 1, 0, 1;\n}"
               : R128(d, e) : "l"(da), "l"(db), "r"(sc));
}
__device__ __forceinline__ void mma256_rs(float (&d)[64], float (&e)[64], uint32_t a0, uint32_t a1, uint32_t a2, uint32_t a3, uint64_t db) {
  asm volatile("{\n.reg .pred p;\nsetp.ne.b32 p, 1, 0;\n"
               "wgmma.mma_async.sync.aligned.m64n256k16.f32.bf16.bf16 " D128 ", {%128,%129,%130,%131}, %132, p, 1, 1, 1;\n}"
               : R128(d, e) : "r"(a0), "r"(a1), "r"(a2), "r"(a3), "l"(db));
}
template <int N> __device__ __forceinline__ void keep(float (&a)[N]) {
#pragma unroll
  for (int i = 0; i < N; i++) asm volatile("" : "+f"(a[i])::"memory");
}
template <int N> __device__ __forceinline__ void keep(uint32_t (&a)[N]) {
#pragma unroll
  for (int i = 0; i < N; i++) asm volatile("" : "+r"(a[i])::"memory");
}

#define STAMP(idx) do {} while (0)
#define PROF(grp, cond, idx) do {} while (0)

constexpr float SCL2 = 1.4426950408889634f * 0.08838834764831845f;

__device__ __forceinline__ void pack_p(const float (&s)[64], uint32_t (&p)[32]) {
#pragma unroll
  for (int i = 0; i < 32; i++) p[i] = pack_bf(s[2 * i], s[2 * i + 1]);
}

__device__ __forceinline__ void issue_qk(float (&s)[64], uint32_t q0, uint32_t q1, uint32_t kslot) {
  const uint64_t db = make_desc(kslot, 16, 1024), da0 = make_desc(q0, 16, 1024), da1 = make_desc(q1, 16, 1024);
#pragma unroll
  for (int kk = 0; kk < 8; kk++) mma_ss<0>(s, (kk < 4 ? da0 : da1) + (kk & 3) * 2, db + (kk >> 2) * 1024 + (kk & 3) * 2, kk != 0);
}
__device__ __forceinline__ void issue_pv(float (&o)[64], uint32_t (&p)[32], uint32_t vslot, int acc) {
  uint64_t db = make_desc(vslot, 16384, 1024);
#pragma unroll
  for (int kk = 0; kk < 8; kk++)
    mma_rs<1>(o, p[4 * kk], p[4 * kk + 1], p[4 * kk + 2], p[4 * kk + 3], db + kk * 128, kk == 0 ? acc : 1);
}

template <int H>
__device__ __forceinline__ void store_chunk(const float (&a)[64], uint32_t addr) {
#pragma unroll
  for (int i = 8 * H; i < 8 * H + 8; i += 2)
    stmatrix4(addr ^ ((i & 7) << 4), pack_bf(a[4 * i], a[4 * i + 1]), pack_bf(a[4 * i + 2], a[4 * i + 3]),
              pack_bf(a[4 * i + 4], a[4 * i + 5]), pack_bf(a[4 * i + 6], a[4 * i + 7]));
}
template <int H>
__device__ __forceinline__ void store_chunk(const float (&a)[64], float i0, float i1, uint32_t addr) {
#pragma unroll
  for (int i = 8 * H; i < 8 * H + 8; i += 2)
    stmatrix4(addr ^ ((i & 7) << 4), pack_bf(a[4 * i] * i0, a[4 * i + 1] * i0), pack_bf(a[4 * i + 2] * i1, a[4 * i + 3] * i1),
              pack_bf(a[4 * i + 4] * i0, a[4 * i + 5] * i0), pack_bf(a[4 * i + 6] * i1, a[4 * i + 7] * i1));
}
__device__ __forceinline__ float inv_quad_sum(float l) {
  l += __shfl_xor_sync(0xffffffffu, l, 1);
  l += __shfl_xor_sync(0xffffffffu, l, 2);
  return rcp(l);
}

__device__ __forceinline__ void ln_scalars(float mean, float var, float& mb, float& sd) {
  mb = rbf(mean);
  float r; asm("sqrt.approx.ftz.f32 %0, %1;" : "=f"(r) : "f"(rbf(rbf(var) + 1e-5f)));
  sd = rbf(r);
}

__global__ void __cluster_dims__(2, 1, 1) __launch_bounds__(384, 1) fused_kernel(const __grid_constant__ Maps maps, const Ptrs P) {
  extern __shared__ __align__(1024) uint8_t smem_raw[];
  const uint32_t base = smem_u32(smem_raw);
  const int tid = threadIdx.x, lane = tid & 31;
  const int warp = __shfl_sync(0xffffffffu, tid >> 5, 0);
  const int b = blockIdx.x;
  PROF(31, tid == 0, 0);

  if (b >= NMAIN) {
    float* sc = reinterpret_cast<float*>(smem_raw);
    float* red = sc + DM;
    for (int k = tid; k < DM; k += 384) sc[k] = rbf(silu_f(__bfloat162float(P.c[k])));
    __syncthreads();
    if (tid < 256) {
      const int col = 2048 + (b - NMAIN) * 1024 + (tid & 127) * 8, r0 = (tid >> 7) * 512;
      float acc[8];
#pragma unroll
      for (int e = 0; e < 8; e++) acc[e] = 0.f;
#pragma unroll 1
      for (int r = r0; r < r0 + 512; r += HU) {
        uint4 w[HU];
#pragma unroll
        for (int u = 0; u < HU; u++) w[u] = ldg_stream4(P.w_mod + (size_t)(r + u) * NMOD + col);
#pragma unroll
        for (int u = 0; u < HU; u++) {
          float s = sc[r + u];
          acc[0] += s * bf_lo(w[u].x); acc[1] += s * bf_hi(w[u].x); acc[2] += s * bf_lo(w[u].y); acc[3] += s * bf_hi(w[u].y);
          acc[4] += s * bf_lo(w[u].z); acc[5] += s * bf_hi(w[u].z); acc[6] += s * bf_lo(w[u].w); acc[7] += s * bf_hi(w[u].w);
        }
      }
      if (tid >= 128) {
#pragma unroll
        for (int e = 0; e < 8; e++) red[(tid & 127) * 8 + e] = acc[e];
      }
      const uint32_t tag = ld_relaxed(&g_epoch) % 3 + 1;
      bar_sync(1, 256);
      if (tid < 128) {
        uint32_t o[8];
#pragma unroll
        for (int e = 0; e < 8; e++) o[e] = __float_as_uint(rbf(acc[e] + red[tid * 8 + e])) | tag;
        st_relaxed4(g_mod + col, o[0], o[1], o[2], o[3]);
        st_relaxed4(g_mod + col + 4, o[4], o[5], o[6], o[7]);
        const uint4 wr = ldg_nc4(P.w_r + tid * 8);
        const uint32_t wv[4] = {wr.x, wr.y, wr.z, wr.w};
        float dsum = 0.f;
#pragma unroll
        for (int e = 0; e < 8; e++) {
          const float m = bf_hi(o[e]);
          dsum += (b == NMAIN + 2 ? rbf(1.f + m) : m) * ((e & 1) ? bf_hi(wv[e >> 1]) : bf_lo(wv[e >> 1]));
        }
#pragma unroll
        for (int k = 16; k > 0; k >>= 1) dsum += __shfl_xor_sync(0xffffffffu, dsum, k);
        if (lane == 0) st_relaxed(g_mod + (b - NMAIN) * 4 + warp, tagf(dsum, tag));
      }
    }
    PROF(2, tid == 0, 1);
    return;
  }

  const int rank = b & 1;
  const int rb = ((b >> 4) << 1) | rank, cj = (b >> 1) & 7;
  const uint32_t bfull = base + OFF_BAR, bempty = bfull + NSLOT * 8;
  const uint32_t gfull = bempty + NSLOT * 8, gempty = gfull + 32;
  const uint32_t bar_ofull = gempty + 32;
  const uint32_t bar_ofree = bar_ofull + 32;
  const uint32_t bar_par = bar_ofree + 32;
  const uint32_t bar_mod = bar_par + 8;
  const uint32_t bar_pread = bar_mod + 8;
  const uint32_t bar_xres = bar_pread + 8;
  const uint32_t bar_ring = bar_xres + 8;
  const uint32_t bar_box = bar_ring + 24;
  const uint32_t bar_go = bar_box + 96;
  const uint32_t bar_go2 = bar_go + 16;
  const uint32_t bar_cnt = bar_go + 24;
  const uint32_t xfull = bar_go + 40, xempty = xfull + 32;
  const uint32_t bar_hw = xempty + 32, bar_hx = bar_hw + 8;
  const uint32_t bar_hpub = bar_hx + 16;
  const uint32_t bar_win = bar_hpub + 16;
  const uint32_t bar_rx = bar_win + 8;
  const uint32_t bar_sel = bar_rx + 8;
  const uint32_t bar_gate = bar_sel + 8;
  const uint32_t bar_rel = bar_gate + 8;
  const uint32_t bar_od = bar_rel + 8;
  const uint32_t bar_res = bar_go + 8;
  const uint32_t stage = base + OFF_STAGE, par = base + OFF_PAR;

  if (warp == 8 && elect_one()) {
    for (int s = 0; s < NSLOT; s++) { mbar_init(bfull + s * 8, 1); mbar_init(bempty + s * 8, 16); }
    for (int s = 0; s < 4; s++) { mbar_init(gfull + s * 8, 1); mbar_init(gempty + s * 8, 16); mbar_init(xfull + s * 8, 1); mbar_init(xempty + s * 8, 8); mbar_init(bar_ofree + s * 8, 1); mbar_init(bar_ofull + s * 8, 128); }
    mbar_init(bar_par, 64); mbar_init(bar_mod, 256); mbar_init(bar_pread, 2); mbar_init(bar_xres, 1);
    mbar_init(bar_ring, 8); mbar_init(bar_ring + 8, 8); mbar_init(bar_ring + 16, 8);
    mbar_init(bar_go, 1); mbar_init(bar_go2, 1); mbar_init(bar_cnt, 1); mbar_init(bar_cnt + 8, 1); mbar_init(bar_hpub, 8); mbar_init(bar_hpub + 8, 8); mbar_init(bar_res, 1); mbar_init(bar_win, 1); mbar_init(bar_rx, 1); mbar_init(bar_sel, 64); mbar_init(bar_gate, 8); mbar_init(bar_rel, 8); mbar_init(bar_od, 1);
    for (int s = 0; s < 12; s++) mbar_init(bar_box + s * 8, 1);
    asm volatile("fence.mbarrier_init.release.cluster;" ::: "memory");
    prefetch_map(&maps.x); prefetch_map(&maps.wq); prefetch_map(&maps.k); prefetch_map(&maps.v);
  }
  if (warp == 9 && elect_one()) {
    mbar_init(bar_hw, 1); mbar_init(bar_hx, 1); mbar_init(bar_hx + 8, 1);
    asm volatile("fence.mbarrier_init.release.cluster;" ::: "memory");
    mbar_expect_tx(bar_hw, 32768);
    mbar_expect_tx(bar_hx, 16384);
    mbar_expect_tx(bar_hx + 8, 16384);
    const __nv_bfloat16* xs = P.x + (size_t)(rb * 128 + cj * 16) * DM;
    bulk_load(base + 2 * GST_BYTES, xs, 16384, bar_hx);
    tma2d(stage, &maps.wm, (b >> 1) * 32, rank * 512, bar_hw);
    tma2d(stage + 16384, &maps.wm, (b >> 1) * 32, rank * 512 + 256, bar_hw);
    bulk_load(base + 3 * GST_BYTES, xs + 8 * DM, 16384, bar_hx + 8);
  }
  cluster_arrive();

  if (warp >= 8) {
    asm volatile("setmaxnreg.dec.sync.aligned.u32 40;");
    if (warp < 10) bar_arrive(1, 320);
    const uint32_t epoch = ld_relaxed(&g_epoch);
    cluster_wait();
    if (warp == 8) {
      const int kvrow = (cj >> 1) * SK + (SK - WIN);
      int wch = cj * 8 + rank * 2;
#pragma unroll 1
      for (int ps = 0; ps < 3; ps++) {
        const CUtensorMap* mw = ps == 2 ? &maps.wo : &maps.wq;
        const uint32_t xt = ps == 1 ? XT1 : XT2, wt = ps == 0 ? WT0 : (ps == 1 ? WT1 : WT2);
        const int nst = ps == 2 ? 32 : 16;
#pragma unroll 1
        for (int i = 0; i < nst; i++) {
          const uint32_t bf = gfull + (i & 3) * 8;
          const int kt = ps == 2 ? (((cj & 1) * 4 + ((i >> 1) & 3)) * 4 + (i >> 3)) * 2 + (i & 1) : (i + (ps ? 0 : b & 14)) & 15;
          const uint32_t wd = base + unit_of(wt, i & 3) + rank * UNIT, xd = base + unit_of(xt, i & 3);
          const uint8_t* xs = g_act + (uint32_t)(rb * 80 + (ps - 1) * 16 + kt) * UNIT;
          if (ps == 0 && i == HD) mbar_wait(bar_mod, 0);
          const bool xfirst = ps && i < 2;
          if (ps == 2 && i == 0) mbar_wait(bar_ofree + 24, 0);
          if (i == 0) fence_async();
          mbar_wait(gempty + (i & 3) * 8, ((i >> 2) & 1) ^ 1);
          if (elect_one()) {
            mbar_expect_tx(bf, ps ? GST_BYTES : 2 * UNIT);
            if (xfirst) bulk_load_stream(xd, xs, UNIT, bf);
          }
          if (ps && i < 4) mbar_wait(bempty + i * 8, 1);
          if (elect_one()) tma3d_mc<true>(wd, mw, 0, (i == 31 ? kt ^ (rank * 32) : kt) * 64, i == 31 ? cj * 2 : wch, bf);
          if (ps) {
            if (i == 16 || i == 24) { mbar_wait(bar_cnt + i - 16, 0); fence_async(); }
            if (i == RES0) mbar_wait(bar_res, 0);
            if (i == 2) mbar_wait(bar_ofree + (ps - 1) * 16, 0);
            if (elect_one()) {
              if (i == 31) bulk_load(xd, xs, UNIT, bf); else if (!xfirst) bulk_load_stream(xd, xs, UNIT, bf);
              mbar_arrive_pred(bar_go, i == GOST - 1);
              if (PG0 < 16) mbar_arrive_pred(bar_go2, ps == 1 && i == PG0);
              mbar_arrive_pred(bar_od, i == (ps == 1 ? ODS1 : ODS));
              if (i == RES0) mbar_expect_tx(bar_xres, 32768);
              if (i == RES0 || i == RES1) tma2d(base + OFF_RES + (i == RES1) * UNIT, &maps.x, cj * 128 + (i == RES1) * 64, rb * 128, bar_xres);
            }
          }
        }
        if (ps == 2) break;
        wch = ps ? ((wch >> 3) ^ rank) * 2 : wch + 4;
#pragma unroll 1
        for (int u = 0; u < 16; u++) {
          const bool isk = (u == 0) || ((u & 1) && u < 15);
          const int blk = (isk ? (u + 1) >> 1 : (u == 15 ? 7 : (u >> 1) - 1)) & 3;
          const uint32_t sl = base + unit_of(ps ? AT1 : AT0, u & 3) + rank * UNIT, bf = bfull + (u & 3) * 8;
          if (u < 4) mbar_wait(gempty + ((u + 1) >> 1) * 8, 1);
          mbar_wait(bempty + (u & 3) * 8, ((u >> 2) & 1) ^ 1);
          if (elect_one()) {
            mbar_arrive_pred(bar_go2, ps && u + 16 == PG0);
            mbar_expect_tx(bf, SLOT_BYTES);
            tma3d_mc<false>(sl, isk ? &maps.k : &maps.v, 0, kvrow + blk * 128, rank, bf);
          }
        }
      }
      if (elect_one()) mbar_expect_tx(bar_rx, UNIT);
      mbar_wait(bar_rel, 0);
      if (elect_one()) {
        bulk_load_stream(base + UNIT, g_act + (uint32_t)(rb * 80 + 16 + 63 - (cj & 1) * 32) * UNIT, UNIT, bar_rx);
      }
      if (b < NFFN) {
#pragma unroll 1
        for (int u = 0; u < 12; u++) {
          const uint32_t dst = base + unit_of(u < 4 ? FT_G : (u < 8 ? FT_U : FT_D), u & 3);
          if (elect_one()) mbar_expect_tx(bar_box + u * 8, UNIT);
          if (u == FB0 || u == FB1 || u == FB2) mbar_wait(bar_ring + (u == FB2 ? 16 : u == FB1 ? 8 : 0), 0);
          const int fp = u < FPB ? FPACE0 : FPACE;
          if (u >= fp) mbar_wait(bar_box + (u - fp) * 8, 0);
          if (elect_one()) {
            if (u < 8) tma2d(dst, u < 4 ? &maps.wg : &maps.wu, b * 32, (u & 3) * 256, bar_box + u * 8);
            else tma3d(dst, &maps.wd, 0, b * 32, (u - 8) * 4, bar_box + u * 8);
          }
        }
      }
    } else if (warp == 9) {
      const uint32_t target = 8 * (epoch + 1);
      uint32_t hmask = 0;
#pragma unroll 1
      for (int i = 0; i < 16; i++) {
        if (i == HDX) mbar_wait(bar_mod, 0);
        const uint32_t need = i == 15 ? 0xffffu : 1u << ((2 * cj + i) & 15);
        if (i >= NRS && (hmask & need) != need) {
          uint32_t n = 0;
          do { hmask = __ballot_sync(0xffffffffu, ld_acquire(&g_cnt_h[rb * 32 + (lane & 15)]) == epoch + 1); watchdog(n); } while ((hmask & need) != need);
          PROF(1, lane == 0 && i == NRS, 26);
          fence_async();
        }
        mbar_wait(xempty + (i & 3) * 8, ((i >> 2) & 1) ^ 1);
        if (elect_one()) {
          mbar_expect_tx(xfull + (i & 3) * 8, UNIT);
          if (i < NRS) tma2d(base + (i & 3) * GST_BYTES, &maps.x, ((2 * cj + i) & 15) * 64, rb * 128, xfull + (i & 3) * 8);
          else bulk_load_stream(base + (i & 3) * GST_BYTES, g_act + (uint32_t)(rb * 80 + ((2 * cj + i) & 15)) * UNIT, UNIT, xfull + (i & 3) * 8);
        }
      }
      prefetch_map(&maps.wo);
#pragma unroll 1
      for (int t = 0; t < 4; t++) {
        if (t & 1) mbar_wait(bar_od, t >> 1);
#pragma unroll 1
        for (int p = 0; p < 32768 / OPS; p++) {
          const uint32_t w = p / (16384 / OPS), c = (p / (8192 / OPS)) & 1, off = w * 8192 + (p % (8192 / OPS)) * OPS;
          mbar_wait(bar_ofull + (t & 1) * 16 + w * 8, t >> 1);
          if (elect_one()) {
            bulk_store(g_act + (uint32_t)(rb * 80 + 16 + (cj * 4 + t) * 2 + c) * UNIT + off, base + unit_of(QT, 2 * t + c) + off, OPS);
            asm volatile("cp.async.bulk.commit_group;" ::: "memory");
            asm volatile("cp.async.bulk.wait_group.read %0;" ::"n"(OFL) : "memory");
          }
        }
        if (elect_one()) {
          asm volatile("cp.async.bulk.wait_group.read 0;" ::: "memory");
          mbar_arrive(t < 3 ? bar_ofree + t * 8 : bar_res);
          asm volatile("cp.async.bulk.wait_group 0;" ::: "memory");
          fence_async();
          red_release(&g_cnt_o[((rb * 4 + t) * 2 + (cj >> 2)) * 32], 2);
        }
        if (t) {
          wait_counter(&g_cnt_o[(rb * 8 + 2 * t + (cj & 1)) * 32], target);
          if (t & 1) wait_counter(&g_cnt_o[(rb * 8 + (t == 1 ? cj & 1 : 7 - (cj & 1))) * 32], target);
          if (elect_one()) mbar_arrive(t == 1 ? bar_ofree + 24 : bar_cnt + t * 8 - 16);
        }
      }
      PROF(2, lane == 0, 27);
      const uint32_t tag = epoch % 3 + 1;
      const uint32_t* inbox = g_cand + (lane & 15);
      mbar_wait(bar_ring + 16, 0);
      uint32_t c0 = ld_relaxed(inbox), n = 0;
#define CAND_STEP(cv)                                                                                        \
      {                                                                                                      \
        const bool valid = (cv & 3u) == tag, all = __all_sync(0xffffffffu, valid);                           \
        const uint32_t best = __reduce_max_sync(0xffffffffu, valid ? cv : 0u);                               \
        const uint32_t blk = __ffs(__ballot_sync(0xffffffffu, cv == best)) - 1;                              \
        if (best) sts2(par + PAR_CONST + 56, best, (blk << 7 | (~best >> 2 & 127)) | (all ? 0x1800 : 0x800)); \
        if (all) break;                                                                                      \
        cv = ld_relaxed(inbox);                                                                              \
      }
      while (true) { CAND_STEP(c0) watchdog(n); }
    } else {
      const int t2 = tid - 320;
      mbar_wait(bar_hpub + (warp & 1) * 8, 0);
      PROF(1, t2 == 0, 24);
#pragma unroll 1
      for (int c = 0; c < 8; c++) {
        const uint32_t off = (warp & 1) * UNIT + c * 2048 + lane * 16;
        uint8_t* dst = g_act + (uint32_t)(rb * 80 + cj * 2) * UNIT + off;
        const uint4 v0 = lds4(stage + off), v1 = lds4(stage + off + 512), v2 = lds4(stage + off + 1024), v3 = lds4(stage + off + 1536);
        stg4(dst, v0); stg4(dst + 512, v1); stg4(dst + 1024, v2); stg4(dst + 1536, v3);
      }
      __syncwarp();
      PROF(1, t2 == 0, 15);
      if (lane == 0) {
        mbar_arrive(bar_pread);
        red_release(&g_cnt_h[rb * 32 + cj * 2 + (warp & 1)], 1);
        PROF(1, t2 == 0, 25);
        prefetch_map(&maps.wg); prefetch_map(&maps.wu); prefetch_map(&maps.wd); prefetch_map(&maps.out);
      }
      __syncwarp();
      if (b < NFFN) {
        mbar_wait(bar_go2, 0);
        const __nv_bfloat16* pg = ((b & 1) ? P.w_up : P.w_gate) + (b >> 1) * 64 + (size_t)t2 * FF;
        const __nv_bfloat16* pd = P.w_down + (size_t)b * 32768 + t2 * 64;
        PROF(2, t2 == 0, 13);
#pragma unroll 1
        for (int i = 0; i < WN; i += WB) {
          uint32_t v[WB];
#pragma unroll
          for (int u = 0; u < WB; u++) {
            const int k = i + u;
            asm volatile("ld.global.cg.L2::128B.u32 %0, [%1];" : "=r"(v[u]) : "l"(k < 16 ? pg + (size_t)k * 64 * FF : pd + (k - 16) * 4096));
          }
#pragma unroll
          for (int u = 1; u < WB; u++) v[0] ^= v[u];
          sts1(par + PAR_SINK + t2 * 4, v[0]);
        }
        PROF(2, t2 == 0, 14);
      }
      const uint32_t tag = epoch % 3 + 1;
      mbar_wait(bar_go, 0);
      bar_sync(4, 64);
      if (warp == 10) {
        const uint32_t* src = g_mod + 2 * DM + cj * 128 + lane * 4;
        const uint2 wr = *reinterpret_cast<const uint2*>(P.w_r + cj * 128 + lane * 4);
        uint4 vga, vsb, vcb, vgb;
        uint32_t n = 0;
        do {
          vga = ld_relaxed4(src); vsb = ld_relaxed4(src + DM); vcb = ld_relaxed4(src + 2 * DM); vgb = ld_relaxed4(src + 3 * DM);
          watchdog(n);
        } while (!__all_sync(0xffffffffu, tag_ok(vga, tag) && tag_ok(vsb, tag) && tag_ok(vcb, tag) && tag_ok(vgb, tag)));
        const float c0 = rbf(1.f + bf_hi(vcb.x)), c1 = rbf(1.f + bf_hi(vcb.y)), c2 = rbf(1.f + bf_hi(vcb.z)), c3 = rbf(1.f + bf_hi(vcb.w));
        const float a0 = c0 * bf_lo(wr.x), a1 = c1 * bf_hi(wr.x), a2 = c2 * bf_lo(wr.y), a3 = c3 * bf_hi(wr.y);
        const uint32_t h0 = pack_bf(a0, a1), h1 = pack_bf(a2, a3);
        const uint32_t t1 = par + PAR_T1 + (lane >> 2) * 64 + (lane & 1) * 32 + (lane & 2) * 2;
        sts1(t1, h0); sts1(t1 + 8, pack_bf(a0 - bf_lo(h0), a1 - bf_hi(h0)));
        sts1(t1 + 16, h1); sts1(t1 + 24, pack_bf(a2 - bf_lo(h1), a3 - bf_hi(h1)));
        const uint32_t tg = par + PAR_SINK + (lane >> 3) * 64 + (lane & 1) * 32 + (lane & 6) * 2;
        sts1(tg, __byte_perm(vga.x, vga.y, 0x7632)); sts1(tg + 16, __byte_perm(vga.z, vga.w, 0x7632));
        sts4(par + PAR_T2 + lane * 32, make_uint4(pack_bf(c0, c1), __byte_perm(vsb.x, vsb.y, 0x7632), __byte_perm(vgb.x, vgb.y, 0x7632), __byte_perm(vga.x, vga.y, 0x7632)));
        sts4(par + PAR_T2 + lane * 32 + 16, make_uint4(pack_bf(c2, c3), __byte_perm(vsb.z, vsb.w, 0x7632), __byte_perm(vgb.z, vgb.w, 0x7632), __byte_perm(vga.z, vga.w, 0x7632)));
      } else {
        const uint4 g = poll4((lane & 2) ? g_mod + 8 - (lane & 1) * 4 : g_mod + 5 * DM + b * 8 + (lane & 1) * 4, tag);
        sts1(par + PAR_CONST + 60, 0);
        if (lane < 2) sts4(par + PAR_CONST + 16 + lane * 16, g);
        else if (lane < 4) sts2(par + PAR_CONST + (lane - 2) * 8, __float_as_uint(untag_sum(g.x, g.y) + untag_sum(g.z, g.w)), epoch);
      }
      __syncwarp();
#pragma unroll 4
      for (int q = 0; q < 32; q++) st_b128(g_xch + ((size_t)b * 8 * 256 + q * 64 + t2) * 4, (epoch & 1) << 16, 0, 0, 0);
      for (int q = 0; q < 2; q++) st_relaxed4(g_stats + ((size_t)cj * SEQ + rb * 128 + q * 64 + t2) * 4, 0, 0, 0, 0);
      if (b < NFFN)
        for (int q = 0; q < 4; q++) st_relaxed4(g_ypart + ((size_t)(q * 32 + (t2 >> 1)) * NFFN + b) * 8 + (t2 & 1) * 4, 0, 0, 0, 0);
      st_relaxed4(g_row + rb * 2 * DM + (t2 >> 5) * DM + cj * 128 + (t2 & 31) * 4, 0, 0, 0, 0);
      __threadfence();
      mbar_arrive(bar_par);
      mbar_wait(bar_gate, 0);
      uint32_t have = 0, n = 0;
      while (true) {
        const uint32_t st = lds1(par + PAR_CONST + 60) >> 7;
        if ((st & 31) != have) {
          const uint32_t* hsrc = g_row + (st & 15) * 2 * DM + t2 * 4;
          uint4 hv[4];
          bool ok = true;
#pragma unroll
          for (int i = 0; i < 4; i++) hv[i] = ld_pairs(hsrc + i * 256);
#pragma unroll
          for (int i = 0; i < 4; i++) {
            sts2(base + ((FT_G >> i * 4) & 15) * UNIT + (warp & 1) * 8192 + 256 + lane * 8, hv[i].x, hv[i].z);
            ok = ok && hv[i].y == tag && hv[i].w == tag;
          }
          have = __all_sync(0xffffffffu, ok) ? st & 31 : 0;
        }
        if ((st ^ have) == 32) break;
        watchdog(n);
      }
      mbar_arrive(bar_sel);
    }
    __syncwarp();
    cluster_arrive();
    {
      const uint32_t tag = epoch % 3 + 1, t3 = tid - 256;
      mbar_wait(bar_win, 0);
      uint2 win = lds2(par + PAR_CONST + 56);
      win.y &= 0x7ff;
      const uint32_t* fsrc = g_row + (win.y >> 7) * 2 * DM + (b >> 1) * 16 + (t3 & 3) * 4 + (b & 1) * 2;
      const uint32_t* ysrc = g_ypart + (size_t)b * NFFN * 8 + min(t3, NFFN - 1) * 4;
      uint2 fh = ld_pair(fsrc), fx = ld_pair(fsrc + DM);
      if (PSL) __nanosleep(PSL);
      uint4 ya = ld_relaxed4(ysrc), yb = ld_relaxed4(ysrc + NFFN * 4);
      const float rwin = __uint_as_float(((int)win.x < 0 ? win.x & 0x7fffffffu : ~win.x) & ~0x1ffu);
      const float rs = rbf(rcp(1.f + __expf(-rbf(rwin))));
      uint32_t n = 0;
      while (__any_sync(0xffffffffu, fh.y != tag || fx.y != tag)) { fh = ld_pair(fsrc); fx = ld_pair(fsrc + DM); watchdog(n); }
      while (!__all_sync(0xffffffffu, tag_ok(ya, tag) && tag_ok(yb, tag))) {
        if (!tag_ok(ya, tag)) ya = ld_relaxed4(ysrc);
        if (!tag_ok(yb, tag)) yb = ld_relaxed4(ysrc + NFFN * 4);
        watchdog(n);
      }
      __syncwarp();
      PROF(8, t3 == 0, 5);
      float y0 = untag_sum(ya.x, yb.x), y1 = untag_sum(ya.y, yb.y), y2 = untag_sum(ya.z, yb.z), y3 = untag_sum(ya.w, yb.w);
      const bool u1 = lane & 2, u2 = lane & 4;
      y0 = (u1 ? y2 : y0) + __shfl_xor_sync(0xffffffffu, u1 ? y0 : y2, 2);
      y1 = (u1 ? y3 : y1) + __shfl_xor_sync(0xffffffffu, u1 ? y1 : y3, 2);
      y0 = (u2 ? y1 : y0) + __shfl_xor_sync(0xffffffffu, u2 ? y0 : y1, 4);
      y0 += __shfl_xor_sync(0xffffffffu, y0, 8);
      if (!(lane & 8)) sts1(par + PAR_RED + 64 + (t3 >> 4) * 32 + ((lane & 1) * 4 + (lane & 2) + ((lane >> 2) & 1)) * 4, __float_as_uint(y0));
      bar_sync(4, 128);
      if (t3 < 4) {
        y0 = 0.f; y1 = 0.f;
#pragma unroll
        for (int w4 = 0; w4 < 7; w4++) {
          const uint2 v = lds2(par + PAR_RED + 64 + w4 * 32 + t3 * 8);
          y0 += __uint_as_float(v.x); y1 += __uint_as_float(v.y);
        }
        const uint2 gv = lds2(par + PAR_CONST + 16 + t3 * 8);
        const uint32_t upd = hmul2(pack_bf(y0, y1), pack_bf(rs, rs));
        *reinterpret_cast<uint32_t*>(P.out + (size_t)win.y * DM + b * 8 + t3 * 2) =
            hadd2(fx.x, hmul2(__byte_perm(gv.x, gv.y, 0x7632), hadd2(fh.x, upd)));
        if (b == 0 && t3 == 0) st_relaxed(&g_epoch, epoch + 1);
      }
      PROF(31, t3 == 0, 36);
    }
    cluster_wait();
  } else {
    const int wg = warp >> 2;

    uint32_t tag;
    {
      uint32_t* const pmod = g_modp + rank * 2 * DM + (b >> 1) * 32 + lane;
      uint32_t* const pln = g_ln1 + (rb * 128 + cj * 16 + warp) * 4;
      const uint32_t cv = ldg_nc1(P.c + rank * 512 + tid * 2);
      const uint32_t epoch = ld_relaxed(&g_epoch);
      if (warp == 0) st_relaxed(pmod, 0);
      if (lane == 0) { st_b128(pln, 0, 0, 0, 0); st_b128(pln + 32, 0, 0, 0, 0); }
      asm volatile("setmaxnreg.inc.sync.aligned.u32 232;");
      sts1(par + tid * 4, pack_bf(silu_f(bf_lo(cv)), silu_f(bf_hi(cv))));
      bar_sync(1, 320);
      tag = epoch % 3 + 1;
#pragma unroll
      for (int part = 0; part < 3; part++) {
        if (part != 1) {
          const uint32_t xa = base + (2 + part / 2) * GST_BYTES + warp * 2048 + lane * 16;
          mbar_wait(bar_hx + part * 4, 0);
          float s0 = 0.f, s1 = 0.f, q0 = 0.f, q1 = 0.f;
#pragma unroll
          for (int q = 0; q < 4; q++) {
            const uint4 xv = lds4(xa + q * 512);
            const uint32_t u[4] = {xv.x, xv.y, xv.z, xv.w};
#pragma unroll
            for (int e = 0; e < 4; e++) { const float lo = bf_lo(u[e]), hi = bf_hi(u[e]); s0 += lo; s1 += hi; q0 += lo * lo; q1 += hi * hi; }
          }
          s0 += s1; q0 += q1;
#pragma unroll
          for (int o = 16; o > 0; o >>= 1) { s0 += __shfl_xor_sync(0xffffffffu, s0, o); q0 += __shfl_xor_sync(0xffffffffu, q0, o); }
          const float mean = s0 * (1.f / DM);
          float mb, sd;
          ln_scalars(mean, fmaxf(q0 * (1.f / DM) - mean * mean, 0.f), mb, sd);
          uint32_t ih, il;
          split_inv(sd, ih, il);
          if (lane == 0) st_b128(pln + part * 16, pack_bf(mb, mb), ih, il, tag);
          PROF(1, tid == 0 && part == 2, 4);
        } else {
          const uint32_t fr = (lane & 7) + (lane >> 4) * 8, tq = lane & 3;
          const uint32_t wa = stage + warp * 4096 + fr * 64 + ((((lane >> 3) & 1) ^ ((fr >> 1) & 3)) << 4);
          uint32_t sc[8];
#pragma unroll
          for (int k = 0; k < 8; k++) sc[k] = lds1(par + warp * 128 + k * 16 + tq * 4);
          float d0[4] = {0.f, 0.f, 0.f, 0.f}, d1[4] = {0.f, 0.f, 0.f, 0.f};
          mbar_wait(bar_hw, 0);
#pragma unroll
          for (int ks = 0; ks < 4; ks++) {
            uint32_t w[8];
            ldmatrix4t(wa + ks * 1024, w[0], w[1], w[2], w[3]);
            ldmatrix4t((wa ^ 32) + ks * 1024, w[4], w[5], w[6], w[7]);
            mma16816(d0, w[0], w[1], w[2], w[3], sc[2 * ks], sc[2 * ks + 1]);
            mma16816(d1, w[4], w[5], w[6], w[7], sc[2 * ks], sc[2 * ks + 1]);
          }
          sts1(base + 2 * GST_BYTES + warp * 2048 + (tq * 8 + (lane >> 2)) * 4, __float_as_uint((tq & 2) ? ((tq & 1) ? d1[2] : d1[0]) : ((tq & 1) ? d0[2] : d0[0])));
          bar_sync(1, 256);
          if (warp == 0) {
            float s = 0.f;
#pragma unroll
            for (int w8 = 0; w8 < 8; w8++) s += __uint_as_float(lds1(base + 2 * GST_BYTES + w8 * 2048 + lane * 4));
            st_relaxed(pmod, (__float_as_uint(s) & ~3u) | tag);
          }
          PROF(1, tid == 0, 3);
        }
      }
      cluster_wait();
      if (wg == 1) bar_arrive(2, 256);
    }

    float f0 = 0.f, f1 = 0.f;
    const uint32_t rempty = lane < 2 ? mapa(bempty, lane & 1) : 0;
    constexpr uint32_t GE = NSLOT * 8 + 32;
    float o[64], s[64];
#pragma unroll 1
    for (int ps = 0; ps < 3; ps++) {
      {
        const uint32_t xt = ps == 1 ? XT1 : XT2, wt = ps == 1 ? WT1 : WT2;
        const int nst = ps == 2 ? 28 : 14;
        if (ps == 0) {
          float ga[64], gb[64];
#pragma unroll
          for (int i = 0; i < 64; i++) { ga[i] = 0.f; gb[i] = 0.f; }
          uint32_t a[2][16];
          const uint32_t l = fresh_lane();
          uint32_t fa[4];
#pragma unroll
          for (int kk = 0; kk < 4; kk++) fa[kk] = (base + wg * 8192 + frag_offset(warp)) ^ (kk * 32);
          const uint32_t mt = par + (l & 3) * 16;
          auto fetch = [&](int i, uint32_t (&f)[16], uint32_t z) {
            mbar_wait(xfull + (i & 3) * 8, i >> 2);
#pragma unroll
            for (int kk = 0; kk < 4; kk++) ldmatrix4(fa[kk] + (i & 3) * GST_BYTES + z, f[4 * kk], f[4 * kk + 1], f[4 * kk + 2], f[4 * kk + 3]);
          };
          uint4 r0, r1;
          {
            const uint32_t t7 = (warp & 3) * 32 + l;
            const uint32_t* pm = g_modp + wg * DM + ((cj * 128 + t7 * 4) & (DM - 1));
            const uint32_t* pr = g_ln1 + (rb * 128 + warp * 16 + (l >> 2)) * 4;
            uint4 m0 = ld_relaxed4(pm), m1 = ld_relaxed4(pm + 2 * DM);
            r0 = ld_b128(pr); r1 = ld_b128(pr + 32);
            fetch(0, a[0], 0); fetch(1, a[1], 0);
            uint32_t n = 0;
            bool written = false;
#pragma unroll 1
            while (true) {
              uint32_t miss;
              asm volatile("{ .reg .pred p0, p1, p2, p3; .reg .b32 t, u;\n"
                           "lop3.b32 t, %1, %2, %19, 0x7e; lop3.b32 u, %3, %4, %19, 0x7e; or.b32 t, t, u; and.b32 t, t, 3; setp.ne.u32 p0, t, 0;\n"
                           "lop3.b32 t, %5, %6, %19, 0x7e; lop3.b32 u, %7, %8, %19, 0x7e; or.b32 t, t, u; and.b32 t, t, 3; setp.ne.u32 p1, t, 0;\n"
                           "setp.ne.u32 p2, %12, %19; setp.ne.u32 p3, %16, %19;\n"
                           "@p0 ld.relaxed.gpu.global.v4.u32 {%1, %2, %3, %4}, [%17];\n"
                           "@p1 ld.relaxed.gpu.global.v4.u32 {%5, %6, %7, %8}, [%17 + 8192];\n"
                           "@p2 ld.relaxed.gpu.global.v4.u32 {%9, %10, %11, %12}, [%18];\n"
                           "@p3 ld.relaxed.gpu.global.v4.u32 {%13, %14, %15, %16}, [%18 + 128];\n"
                           "or.pred p0, p0, p1; or.pred p2, p2, p3; vote.sync.any.pred p0, p0, 0xffffffff; vote.sync.any.pred p2, p2, 0xffffffff;\n"
                           "selp.u32 t, 1, 0, p0; selp.u32 u, 2, 0, p2; or.b32 %0, t, u; }"
                           : "=r"(miss), "+r"(m0.x), "+r"(m0.y), "+r"(m0.z), "+r"(m0.w), "+r"(m1.x), "+r"(m1.y), "+r"(m1.z), "+r"(m1.w),
                             "+r"(r0.x), "+r"(r0.y), "+r"(r0.z), "+r"(r0.w), "+r"(r1.x), "+r"(r1.y), "+r"(r1.z), "+r"(r1.w)
                           : "l"(pm), "l"(pr), "r"(tag) : "memory");
              if (!(miss & 1) && !written) {
                written = true;
                float c0 = untag_sum(m0.x, m1.x), c1 = untag_sum(m0.y, m1.y), c2 = untag_sum(m0.z, m1.z), c3 = untag_sum(m0.w, m1.w);
                if (wg) { c0 = 1.f + rbf(c0); c1 = 1.f + rbf(c1); c2 = 1.f + rbf(c2); c3 = 1.f + rbf(c3); }
                const uint32_t d = par + (t7 >> 2) * 64 + (t7 & 1) * 32 + (t7 & 2) * 2 + (wg ? 0 : 8);
                sts1(d, pack_bf(c0, c1));
                sts1(d + 16, pack_bf(c2, c3));
                mbar_arrive(bar_mod);
              }
              if (!miss) break;
              watchdog(n);
            }
          }
          const uint32_t zero = r0.w ^ tag;
          auto normalize = [&](uint32_t (&f)[16]) {
#pragma unroll
            for (int k = 0; k < 16; k += 2) { f[k] = ln_norm(f[k], r0.x, r0.y, r0.z); f[k + 1] = ln_norm(f[k + 1], r1.x, r1.y, r1.z); }
          };
          auto modulate = [&](int i, uint32_t (&f)[16]) {
#pragma unroll
            for (int kk = 0; kk < 4; kk++) {
              const uint4 m = lds4(mt + i * 256 + kk * 64);
              f[4 * kk] = MODUL(f[4 * kk], m.x, m.z); f[4 * kk + 1] = MODUL(f[4 * kk + 1], m.x, m.z);
              f[4 * kk + 2] = MODUL(f[4 * kk + 2], m.y, m.w); f[4 * kk + 3] = MODUL(f[4 * kk + 3], m.y, m.w);
            }
            keep(f);
            mbar_arrive_pred(xempty + (i & 3) * 8, l == 0);
          };
          auto publish = [&](int u, uint32_t (&f)[16]) {
#pragma unroll
            for (int kk = 0; kk < 4; kk++) stmatrix4(fa[kk] + OFF_STAGE + u * UNIT, f[4 * kk], f[4 * kk + 1], f[4 * kk + 2], f[4 * kk + 3]);
            __syncwarp();
            mbar_arrive_pred(bar_hpub + u * 8, l == 0);
          };
          auto multiply = [&](int i, uint32_t (&f)[16]) {
            mbar_wait(gfull + (i & 3) * 8, i >> 2);
            const uint64_t db = make_desc(base + (i & 3) * GST_BYTES + UNIT, 8192, 1024);
            wg_fence();
#pragma unroll
            for (int kk = 0; kk < 4; kk++) mma256_rs(ga, gb, f[4 * kk], f[4 * kk + 1], f[4 * kk + 2], f[4 * kk + 3], db + kk * 128);
            wg_commit();
          };
          auto next = [&](int i, uint32_t (&f)[16]) {
            wg_wait<1>();
            mbar_arrive_cl(rempty, GE + ((i + 2) & 3) * 8);
            uint32_t z = zero;
#pragma unroll
            for (int k = 0; k < 16; k += 2) asm volatile("lop3.b32 %0, %1, %2, %0, 0xA8;" : "+r"(z) : "r"(f[k]), "r"(f[k + 1]));
            fetch(i, f, z);
            normalize(f); modulate(i, f); multiply(i, f);
          };
          normalize(a[0]); normalize(a[1]);
          keep(a[0]); keep(a[1]);
          mbar_wait(bar_mod, 0);
          PROF(1, tid == 0, 2);
          modulate(0, a[0]); multiply(0, a[0]); publish(0, a[0]);
          modulate(1, a[1]); multiply(1, a[1]); publish(1, a[1]);
#pragma unroll 1
          for (int i = 2; i < NRS; i += 2) { next(i, a[0]); next(i + 1, a[1]); }
          wg_wait<1>();
          mbar_arrive_cl(rempty, GE + ((NRS + 2) & 3) * 8);
#pragma unroll 1
          for (int i = NRS; i < 14; i++) {
            mbar_wait(xfull + (i & 3) * 8, (i >> 2) & 1);
            mbar_wait(gfull + (i & 3) * 8, (i >> 2) & 1);
            const uint32_t xa = base + (i & 3) * GST_BYTES;
            const uint64_t da = make_desc(xa + wg * 8192, 16, 1024), db = make_desc(xa + UNIT, 8192, 1024);
            if (i == 13) bar_sync(2 + wg, 256);
            wg_fence();
#pragma unroll
            for (int kk = 0; kk < 4; kk++) mma256_ss(ga, gb, da + kk * 2, db + kk * 128, 1);
            wg_commit();
            if (i == 13) bar_arrive(3 - wg, 256);
            wg_wait<1>();
            uint32_t z = zero;
#pragma unroll
            for (int k = 0; k < 16; k += 2) asm volatile("lop3.b32 %0, %1, %2, %0, 0xA8;" : "+r"(z) : "r"(a[1][k]), "r"(a[1][k + 1]));
            mbar_arrive_cl(rempty, GE + ((i + 3) & 3) * 8 + z);
            mbar_arrive_pred(xempty + ((i + 3) & 3) * 8, l == 0 && i != NRS);
          }
          mbar_wait(xfull + 16, 1);
          wg_wait<0>();
          keep(ga); keep(gb);
#pragma unroll
          for (int i = 0; i < 64; i++) {
            asm volatile("mov.b32 %0, %1;" : "=f"(s[i]) : "f"(ga[i]));
            asm volatile("mov.b32 %0, %1;" : "=f"(o[i]) : "f"(gb[i]));
          }
        } else {
          float ga[64], gb[64];
#pragma unroll
          for (int i = 0; i < 64; i++) {
            asm volatile("mov.b32 %0, %1;" : "=f"(ga[i]) : "f"(s[i]));
            asm volatile("mov.b32 %0, %1;" : "=f"(gb[i]) : "f"(o[i]));
          }
#pragma unroll 1
          for (int i = 0; i < nst; i++) {
            mbar_wait(gfull + (i & 3) * 8, (i >> 2) & 1);
            const uint64_t da = make_desc(base + unit_of(xt, i & 3) + wg * 8192, 16, 1024), db = make_desc(base + unit_of(wt, i & 3), 8192, 1024);
            if (i == nst - 1) bar_sync(2 + wg, 256);
            wg_fence();
#pragma unroll
            for (int kk = 0; kk < 4; kk++) mma256_ss(ga, gb, da + kk * 2, db + kk * 128, kk ? 1 : i);
            wg_commit();
            if (i == nst - 1) bar_arrive(3 - wg, 256);
            wg_wait<1>();
            mbar_arrive_cl(rempty, GE + ((i + 3) & 3) * 8, i != 0);
            PROF(4, tid == 0 && (i & 3) == 0, 40 + (ps - 1) * 4 + i / 4);
          }
          wg_wait<0>();
          keep(ga); keep(gb);
#pragma unroll
          for (int i = 0; i < 64; i++) {
            asm volatile("mov.b32 %0, %1;" : "=f"(s[i]) : "f"(ga[i]));
            asm volatile("mov.b32 %0, %1;" : "=f"(o[i]) : "f"(gb[i]));
          }
        }
        mbar_arrive_cl(rempty, GE + (ps == 2 ? 24 : 8));
        if (ps == 2) break;
      }
      const uint32_t qw = base + wg * 8192, qt = QT >> (16 * ps), at = ps ? AT1 : AT0;
      {
        const uint32_t wt = ps ? WT1 : WT0;
        const uint64_t da0 = make_desc(qw + unit_of(qt, 2), 16, 1024), da1 = make_desc(qw + unit_of(qt, 3), 16, 1024);
        const uint64_t db0 = make_desc(base + unit_of(wt, 2), 8192, 1024), db1 = make_desc(base + unit_of(wt, 3), 8192, 1024);
        mbar_wait(gfull + 16, 1);
        bar_sync(2 + wg, 256);
        wg_fence();
#pragma unroll
        for (int kk = 0; kk < 4; kk++) mma_ss<1>(s, da0 + kk * 2, db0 + kk * 128, 1);
        wg_commit();
        mbar_wait(xfull + 24, 1);
        mbar_wait(gfull + 24, 1);
        wg_fence();
#pragma unroll
        for (int kk = 0; kk < 4; kk++) mma_ss<1>(s, da1 + kk * 2, db1 + kk * 128, 1);
        wg_commit();
        bar_arrive(3 - wg, 256);
        mbar_wait(ps == 0 ? bar_pread : bar_ofree + 8, 0);
        wg_wait<0>();
        keep(s);
        PROF(2, tid == 0, 8 + ps * 8);
        uint32_t q[32];
        if (QRS) {
          pack_p(s, q);
          const uint32_t a0 = qw + unit_of(qt, 0) + frag_offset(warp), a1 = qw + unit_of(qt, 1) + frag_offset(warp);
#pragma unroll
          for (int i = 0; i < QRS; i++) stmatrix4((i < 4 ? a0 : a1) ^ ((i & 3) << 5), q[4 * i], q[4 * i + 1], q[4 * i + 2], q[4 * i + 3]);
          keep(q);
        } else {
          store_chunk<0>(s, qw + unit_of(qt, 0) + frag_offset(warp));
          store_chunk<1>(s, qw + unit_of(qt, 1) + frag_offset(warp));
          fence_async_smem();
        }
        bar_sync(2 + wg, 256);
        wg_fence();
#pragma unroll
        for (int kk = 0; kk < 8; kk++) mma_ss<1>(o, (kk < 4 ? da0 : da1) + (kk & 3) * 2, (kk < 4 ? db0 : db1) + UNIT / 16 + (kk & 3) * 128, 1);
        wg_commit();
        mbar_wait(bfull, 0);
        wg_fence();
        if (QRS) {
          const uint64_t dk = make_desc(base + unit_of(at, 0), 16, 1024);
#pragma unroll
          for (int kk = 0; kk < 8; kk++) mma_rs<0>(s, q[4 * kk], q[4 * kk + 1], q[4 * kk + 2], q[4 * kk + 3], dk + (kk >> 2) * 1024 + (kk & 3) * 2, kk != 0);
        } else {
          issue_qk(s, qw + unit_of(qt, 0), qw + unit_of(qt, 1), base + unit_of(at, 0));
        }
        wg_commit();
        bar_arrive(3 - wg, 256);
        if (QRS) {
          const uint32_t a0 = qw + unit_of(qt, 0) + frag_offset(warp), a1 = qw + unit_of(qt, 1) + frag_offset(warp);
#pragma unroll
          for (int i = QRS; i < 8; i++) stmatrix4((i < 4 ? a0 : a1) ^ ((i & 3) << 5), q[4 * i], q[4 * i + 1], q[4 * i + 2], q[4 * i + 3]);
        }
        wg_wait<1>();
        keep(o);
        mbar_arrive_cl(rempty, GE + 16);
        mbar_arrive_cl(rempty, GE + 24);
        store_chunk<0>(o, qw + unit_of(qt, 2) + frag_offset(warp));
        store_chunk<1>(o, qw + unit_of(qt, 3) + frag_offset(warp));
        wg_wait<0>();
        keep(s);
        mbar_arrive_cl(rempty, 0);
      }
      PROF(4, tid == 0 && ps == 1, 61);
      float l0 = 0.f, l1 = 0.f;
      auto step = [&](auto odd_c, const int j, uint32_t (&pw)[32], uint32_t (&pr)[32]) {
        constexpr bool ODD = decltype(odd_c)::value;
        const bool first = !ODD && (j & 2) == 0, last = ODD && j == 7;
        const uint32_t ph = (j >> 1) & 1;
        float i0, i1, a0, a1;
        const bool so = !ODD && j == 4;
        if (so) { i0 = inv_quad_sum(l0); i1 = inv_quad_sum(l1); l0 = 0.f; l1 = 0.f; }
        bool redo = !ODD && (j | ps) == 0;
        while (true) {
          if (redo) {
            float m0 = fmaxf(s[0], s[1]), m1 = fmaxf(s[2], s[3]);
#pragma unroll
            for (int i = 1; i < 16; i++) { m0 = fmaxf(m0, fmaxf(s[4 * i], s[4 * i + 1])); m1 = fmaxf(m1, fmaxf(s[4 * i + 2], s[4 * i + 3])); }
            m0 = fmaxf(m0, __shfl_xor_sync(0xffffffffu, m0, 1)); m1 = fmaxf(m1, __shfl_xor_sync(0xffffffffu, m1, 1));
            m0 = fmaxf(m0, __shfl_xor_sync(0xffffffffu, m0, 2)); m1 = fmaxf(m1, __shfl_xor_sync(0xffffffffu, m1, 2));
            m0 *= SCL2; m1 *= SCL2;
            if (!first) {
              m0 = fmaxf(m0, f0); m1 = fmaxf(m1, f1);
              const float c0 = ex2(f0 - m0), c1 = ex2(f1 - m1);
              l0 *= c0; l1 *= c1;
              wg_wait<0>();
              keep(o);
#pragma unroll
              for (int i = 0; i < 16; i++) { o[4 * i] *= c0; o[4 * i + 1] *= c0; o[4 * i + 2] *= c1; o[4 * i + 3] *= c1; }
            }
            f0 = m0; f1 = m1;
          }
          float b0 = 0.f, b1 = 0.f;
          a0 = 0.f; a1 = 0.f;
#pragma unroll
          for (int i = 0; i < 16; i++) {
            const float e0 = ex2(fmaf(s[4 * i], SCL2, -f0)), e1 = ex2(fmaf(s[4 * i + 1], SCL2, -f0));
            const float e2 = ex2(fmaf(s[4 * i + 2], SCL2, -f1)), e3 = ex2(fmaf(s[4 * i + 3], SCL2, -f1));
            a0 += e0; b0 += e1; a1 += e2; b1 += e3;
            pw[2 * i] = pack_bf(e0, e1); pw[2 * i + 1] = pack_bf(e2, e3);
            if (i == VREL) {
#pragma unroll
              for (int k = 0; k < 2 * VREL + 2; k++) asm volatile("" : "+r"(pw[k])::"memory");
              mbar_wait(bar_mod, 0);
              wg_wait<0>();
              mbar_arrive_cl(rempty, ODD ? 16 : 0, !redo && (ODD || j));
#pragma unroll
              for (int k = 4 * VREL + 4; k < 64; k++) asm volatile("" : "+f"(s[k])::"memory");
            }
          }
          a0 += b0; a1 += b1;
          if (redo) break;
          redo = __any_sync(0xffffffffu, !(a0 + a1 < 0x1p90f));
          if (first) {
            uint32_t m0 = __ballot_sync(0xffffffffu, a0 > 0x1p-80f), m1 = __ballot_sync(0xffffffffu, a1 > 0x1p-80f);
            m0 |= m0 >> 1; m1 |= m1 >> 1; m0 |= m0 >> 2; m1 |= m1 >> 2;
            redo = redo || (m0 & m1 & 0x11111111u) != 0x11111111u;
          }
          if (!redo) break;
        }
        l0 += a0; l1 += a1;
        keep(pw);
        keep(o);
        if (so) store_chunk<0>(o, i0, i1, qw + unit_of(qt, 0) + frag_offset(warp));
        keep(o);
        if (QRS ? (ODD ? j == 5 : j == 0) : ODD && !(j & 2)) { fence_async_smem(); if (ODD) mbar_arrive_pred(bar_ofull + wg * 8, j > 4); }
        mbar_wait(bfull + (ODD ? 24 : 8), ph);
        bar_sync(2 + wg, 256);
        if (!last) {
          const uint32_t qn = qt >> (j >= 3 ? 8 : 0);
          wg_fence();
          issue_qk(s, qw + unit_of(qn, 0), qw + unit_of(qn, 1), base + unit_of(at, ODD ? 3 : 1));
          wg_commit();
          mbar_wait(bfull + (ODD ? 0 : 16), ODD ? ph ^ 1 : ph);
        }
        if (so) { store_chunk<1>(o, i0, i1, qw + unit_of(qt, 1) + frag_offset(warp)); keep(o); }
        wg_fence();
        issue_pv(o, pw, base + unit_of(at, ODD ? (last ? 3 : 0) : 2), !first);
        wg_commit();
        bar_arrive(3 - wg, 256);
        wg_wait<1>();
        keep(s);
        mbar_arrive_cl(rempty, ODD ? 24 : 8, !last);
        PROF(4, tid == 0 && ps == 1, 51 + j);
      };
      uint32_t pa[32], pb[32];
#pragma unroll 1
      for (int j = 0; j < 8; j += 2) {
        step(std::false_type{}, j, pa, pb);
        step(std::true_type{}, j + 1, pb, pa);
      }
      {
        const float i0 = inv_quad_sum(l0), i1 = inv_quad_sum(l1);
        wg_wait<0>();
        keep(o);
        mbar_arrive_cl(rempty, 24);
        store_chunk<0>(o, i0, i1, qw + unit_of(qt, 2) + frag_offset(warp));
        store_chunk<1>(o, i0, i1, qw + unit_of(qt, 3) + frag_offset(warp));
        fence_async_smem();
        mbar_arrive(bar_ofull + 16 + wg * 8);
      }
      PROF(2, tid == 0, 10 + ps * 8);
    }

    const int ln = fresh_lane(), g = ln >> 2, tq = ln & 3, ct = warp * 32 + ln;
    const bool lane0 = ln == 0;
    const int lrow0 = warp * 16 + g;
    const int grow0 = rb * 128 + lrow0;
    const uint32_t res = base + OFF_RES, trow = res + wg * 8192 + frag_offset(warp);
    uint32_t xr[32];
    uint4 sv[4], own;
    uint32_t* sp[4];
#pragma unroll
    for (int k = 0; k < 4; k++) sp[k] = g_stats + ((((tq >> 1) * 4 + k) ^ cj) * SEQ + grow0 + (tq & 1) * 8) * 4;
    {
      const uint64_t da = make_desc(base + wg * 8192, 16, 1024), db = make_desc(base, 8192, 1024);
      constexpr int U = UNIT / 16;
#define HALF_STAGE(acc, xu, wu) _Pragma("unroll") for (int kk = 0; kk < 4; kk++) mma_ss<1>(acc, da + (xu) * U + kk * 2, db + (wu) * U + kk * 128, 1)
      PROF(10, ct == PT, 19); STAMP(0);
      cluster_arrive();
      mbar_wait(gfull, 1);
      mbar_wait(gfull + 8, 1);
      bar_sync(2 + wg, 256);
      wg_fence();
      HALF_STAGE(o, 7, 1);
      HALF_STAGE(o, 8, 3);
      wg_commit();
      STAMP(16);
      mbar_wait(gfull + 16, 1);
      STAMP(17);
      wg_fence();
      HALF_STAGE(o, 6, 11);
      wg_commit();
      bar_arrive(3 - wg, 256);
      mbar_wait(bar_par, 0);
      uint32_t* xo = g_xch + ((size_t)b * 8 * 256 + ct) * 4;
      const uint32_t* xi = g_xch + ((size_t)(b ^ 2) * 8 * 256 + ct) * 4;
      const uint32_t par1 = (~lds1(par + PAR_CONST + 4) & 1) << 16;
      wg_wait<1>();
      mbar_arrive_pred(bar_rel, lane0);
      wg_wait<0>();
      keep(o);
      mbar_arrive_pred(bar_ring, lane0);
      PROF(8, ct == PT, 20); STAMP(1);
#define SEND(i) st_b128(xo + (i) * 1024, (pack_bf(o[8 * (i)], o[8 * (i) + 1]) & ~0x10000u) | par1, pack_bf(o[8 * (i) + 2], o[8 * (i) + 3]), \
                        pack_bf(o[8 * (i) + 4], o[8 * (i) + 5]), pack_bf(o[8 * (i) + 6], o[8 * (i) + 7]))
#pragma unroll
      for (int i = 0; i < NS1; i++) SEND(i);
      PROF(8, ct == PT, 21); STAMP(2);
      bar_sync(2 + wg, 256);
      wg_fence();
      HALF_STAGE(s, 7, 0);
      HALF_STAGE(s, 8, 2);
      HALF_STAGE(s, 6, 10);
      wg_commit();
      bar_arrive(3 - wg, 256);
      STAMP(18);
      mbar_wait(gfull + 24, 1);
#pragma unroll
      for (int i = NS1; i < 8; i++) SEND(i);
      uint4 v[8];
#pragma unroll
      for (int i = 0; i < LD1; i++) v[i] = ld_b128(xi + i * 1024);
      STAMP(19);
      mbar_wait(bar_xres, 0);
      wg_wait<0>();
      mbar_arrive_pred(bar_ring + 8, lane0);
      bar_sync(2 + wg, 256);
      STAMP(20);
#pragma unroll
      for (int i = LD1; i < LD2; i++) v[i] = ld_b128(xi + i * 1024);
      mbar_wait(bar_xres, 0);
      wg_fence();
      HALF_STAGE(s, 9, 4);
      wg_commit();
      mbar_wait(bar_rx, 0);
      wg_fence();
      HALF_STAGE(s, 1, 5);
      wg_commit();
      bar_arrive(3 - wg, 256);
      STAMP(21);
#pragma unroll
      for (int i = LD2; i < 8; i++) v[i] = ld_b128(xi + i * 1024);
      if (LD2 < 8) mbar_wait(bar_xres, 0);
      wg_wait<0>();
      keep(s);
      mbar_arrive_pred(bar_ring + 16, lane0);
      PROF(10, ct == PT, 23); STAMP(4);
#pragma unroll
      for (int i = 0; i < 16; i += 2) ldmatrix4((trow ^ ((i & 7) << 4)) + (i >> 3) * 16384, xr[2 * i], xr[2 * i + 1], xr[2 * i + 2], xr[2 * i + 3]);
      uint32_t ga[16];
      uint4 bw[8];
#pragma unroll
      for (int i = 0; i < 8; i++) {
        if (!(i & 1)) {
          const uint4 t = lds4(par + PAR_SINK + i * 32 + tq * 16);
          ga[2 * i] = t.x; ga[2 * i + 1] = t.y; ga[2 * i + 2] = t.z; ga[2 * i + 3] = t.w;
        }
        bw[i] = lds4(par + PAR_T1 + i * 64 + tq * 16);
        if (!(g & 1)) { bw[i].x = 0x3f803f80u; bw[i].y = 0x3f803f80u; }
      }
      uint32_t pk[32];
      pack_p(s, pk);
      keep(pk);
      {
        uint32_t n = 0, miss;
        do {
          miss = 0;
#pragma unroll
          for (int i = 0; i < 8; i++) miss |= v[i].x ^ par1;
          miss = __any_sync(0xffffffffu, miss & 0x10000u);
          if (miss) {
#pragma unroll
            for (int i = 0; i < 8; i++)
              asm volatile("{ .reg .pred p; .reg .b32 t; xor.b32 t, %0, %5; and.b32 t, t, 0x10000; setp.ne.u32 p, t, 0;\n"
                           "@p ld.relaxed.gpu.global.v4.u32 {%0, %1, %2, %3}, [%4]; }"
                           : "+r"(v[i].x), "+r"(v[i].y), "+r"(v[i].z), "+r"(v[i].w) : "l"(xi + i * 1024), "r"(par1) : "memory");
          }
          watchdog(n);
        } while (miss);
      }
      PROF(8, ct == PT, 22); STAMP(3);
      float ds[4] = {0.f, 0.f, 0.f, 0.f}, dl[4] = {0.f, 0.f, 0.f, 0.f}, q0[4] = {0.f, 0.f, 0.f, 0.f}, q1[4] = {0.f, 0.f, 0.f, 0.f};
#pragma unroll
      for (int i = 0; i < 8; i++) {
        const uint32_t u0 = hfma2(ga[2 * i], hadd2(pk[4 * i], v[i].x & ~0x10000u), xr[4 * i]);
        const uint32_t u1 = hfma2(ga[2 * i], hadd2(pk[4 * i + 1], v[i].y), xr[4 * i + 1]);
        const uint32_t u2 = hfma2(ga[2 * i + 1], hadd2(pk[4 * i + 2], v[i].z), xr[4 * i + 2]);
        const uint32_t u3 = hfma2(ga[2 * i + 1], hadd2(pk[4 * i + 3], v[i].w), xr[4 * i + 3]);
        xr[4 * i] = u0; xr[4 * i + 1] = u1; xr[4 * i + 2] = u2; xr[4 * i + 3] = u3;
        mma16816(ds, u0, u1, u2, u3, bw[i].x, bw[i].y);
        mma16816(dl, u0, u1, u2, u3, bw[i].z, bw[i].w);
        mma16816(q0, u0, u1, u2, u3, u0, u2);
        mma16816(q1, u0, u1, u2, u3, u1, u3);
      }
      const float sqa = __shfl_sync(0xffffffffu, (g & 1) ? q0[1] : q0[0], g * 4 + (g >> 1));
      const float sqb = __shfl_sync(0xffffffffu, (g & 1) ? q1[3] : q1[2], g * 4 + (g >> 1));
      own = (tq & 1) ? make_uint4(__float_as_uint(ds[2]), __float_as_uint(sqb), __float_as_uint(ds[3] + dl[3]), tag)
                                 : make_uint4(__float_as_uint(ds[0]), __float_as_uint(sqa), __float_as_uint(ds[1] + dl[1]), tag);
      if (tq < 2) st_b128(sp[0], own.x, own.y, own.z, own.w);
#pragma unroll
      for (int k = 0; k < 4; k++) sv[k] = make_uint4(0, 0, 0, 0);
    }
    PROF(8, ct == PT, 29); STAMP(5);
    uint32_t mm, ih, il;
    float rbest;
    uint32_t wf[128];
    const uint32_t frow = (ln & 7) + (ln >> 4) * 8;
    const uint32_t wfo = base + (warp & 1) * 8192 + frow * 64 + ((((ln >> 3) & 1) ^ ((frow >> 1) & 3)) << 4);
#define LOAD_WF(m) _Pragma("unroll") for (int f = 0; f < 16; f++) {                                                   \
      const int r = ((f >> 1) * 4 + (m) * 2 + (f & 1)) * 4;                                                           \
      ldmatrix4t(((wfo + unit_of((m) ? FT_U : FT_G, warp >> 1)) ^ ((f & 1) * 32)) + (f >> 1) * 1024, wf[r], wf[r + 1], wf[r + 2], wf[r + 3]); \
    }
    bool early;
    {
#pragma unroll
      for (int i = 0; i < 16; i += 2) stmatrix4((trow ^ ((i & 7) << 4)) + (i >> 3) * 16384, xr[2 * i], xr[2 * i + 1], xr[2 * i + 2], xr[2 * i + 3]);
      const uint4 cst = lds4(par + PAR_CONST);
      const float A1 = __uint_as_float(cst.x), A2 = __uint_as_float(cst.z);
      uint32_t n = 0;
      early = false;
#pragma unroll 1
      while (true) {
        uint32_t miss;
        asm volatile("{ .reg .pred p0, p1, p2, p3; .reg .b64 u, v; .reg .b128 w;\n"
                     "setp.ge.u32 p0, %22, 2; setp.ne.and.u32 p0, %4, %21, p0; setp.ne.u32 p1, %8, %21; setp.ne.u32 p2, %12, %21; setp.ne.u32 p3, %16, %21;\n"
                     "@p0 ld.relaxed.gpu.global.v4.u32 {%1, %2, %3, %4}, [%17];\n"
                     "@p1 ld.relaxed.gpu.global.v4.u32 {%5, %6, %7, %8}, [%18];\n"
                     "@p2 ld.relaxed.gpu.global.v4.u32 {%9, %10, %11, %12}, [%19];\n"
                     "@p3 ld.relaxed.gpu.global.v4.u32 {%13, %14, %15, %16}, [%20];\n"
                     "or.pred p0, p0, p1; or.pred p2, p2, p3; or.pred p0, p0, p2; vote.sync.any.pred p0, p0, 0xffffffff; selp.u32 %0, 1, 0, p0; }"
                     : "=r"(miss), "+r"(sv[0].x), "+r"(sv[0].y), "+r"(sv[0].z), "+r"(sv[0].w), "+r"(sv[1].x), "+r"(sv[1].y), "+r"(sv[1].z), "+r"(sv[1].w),
                       "+r"(sv[2].x), "+r"(sv[2].y), "+r"(sv[2].z), "+r"(sv[2].w), "+r"(sv[3].x), "+r"(sv[3].y), "+r"(sv[3].z), "+r"(sv[3].w)
                     : "l"(sp[0]), "l"(sp[1]), "l"(sp[2]), "l"(sp[3]), "r"(tag), "r"(tq) : "memory");
        if (!miss) break;
        if (!early && (b >= NFFN || __all_sync(0xffffffffu, mbar_test(bar_box + (warp >> 1) * 8, 0)))) {
          early = true;
          LOAD_WF(0);
          __syncwarp();
          mbar_arrive_pred(bar_gate, lane0);
        }
        watchdog(n);
      }
      const uint4 v0 = tq < 2 ? own : sv[0], v1 = sv[1], v2 = sv[2], v3 = sv[3];
      PROF(8, ct == PT, 30); STAMP(6);
      float su = (__uint_as_float(v0.x) + __uint_as_float(v1.x)) + (__uint_as_float(v2.x) + __uint_as_float(v3.x));
      float sq = (__uint_as_float(v0.y) + __uint_as_float(v1.y)) + (__uint_as_float(v2.y) + __uint_as_float(v3.y));
      float dt = (__uint_as_float(v0.z) + __uint_as_float(v1.z)) + (__uint_as_float(v2.z) + __uint_as_float(v3.z));
      su += __shfl_xor_sync(0xffffffffu, su, 2); sq += __shfl_xor_sync(0xffffffffu, sq, 2); dt += __shfl_xor_sync(0xffffffffu, dt, 2);
      const float m = su * (1.f / DM);
      float mb, sd;
      ln_scalars(m, fmaxf(sq * (1.f / DM) - m * m, 0.f), mb, sd);
      const float inv = rcp(sd);
      rbest = (dt - mb * A1) * inv + A2;
      mm = pack_bf(mb, mb);
      ih = pack_bf(inv, inv);
      const float lo = inv - bf_lo(ih);
      il = pack_bf(lo, lo);
    }
    int ibest;
    {
      const uint32_t bits = __float_as_uint(rbest);
      const uint32_t key = (((int)bits < 0 ? ~bits : bits | 0x80000000u) & ~0x1ffu) | ((127 - lrow0 - (tq & 1) * 8) << 2) | tag;
      sts1(par + PAR_RED + warp * 4, __reduce_max_sync(0xffffffffu, key));
      PROF(8, ct == PT, 38); STAMP(7);
      bar_sync(1, 256);
      const uint4 ka = lds4(par + PAR_RED), kb = lds4(par + PAR_RED + 16);
      const uint32_t k2 = max(max(max(ka.x, ka.y), max(ka.z, ka.w)), max(max(kb.x, kb.y), max(kb.z, kb.w)));
      if (ct == 0 && cj == 0) st_relaxed(g_cand + rb, k2);
      ibest = 127 - ((k2 >> 2) & 127);
    }
    PROF(8, ct == PT, 39); STAMP(8);
    if ((ibest >> 4) == warp) {
      const int src = (ibest & 7) * 4 + ((ibest >> 3) & 1), ch = g * 2;
      const uint32_t cm = __shfl_sync(0xffffffffu, mm, src), ch_ = __shfl_sync(0xffffffffu, ih, src), cl = __shfl_sync(0xffffffffu, il, src);
      const uint32_t xa = res + (ch >> 3) * 16384 + ibest * 128 + (((ch & 7) ^ (ibest & 7)) << 4) + tq * 4;
      const uint32_t x0 = lds1(xa), x1 = lds1(xa ^ 16);
      const uint2 p0 = lds2(par + PAR_T2 + ch * 64 + tq * 16), p1 = lds2(par + PAR_T2 + ch * 64 + 64 + tq * 16);
      uint32_t* dst = g_row + rb * 2 * DM + cj * 128 + ln * 4;
      st_pairs(dst, ln_mod(x0, cm, ch_, cl, p0.x, p0.y), ln_mod(x1, cm, ch_, cl, p1.x, p1.y), tag);
      st_pairs(dst + DM, x0, x1, tag);
      __syncwarp();
    }
    PROF(8, ct == PT, 37); STAMP(9);
    uint32_t wd[64];
    const uint32_t wda = base + unit_of(FT_D, warp >> 1) + (warp & 1) * 8192 + frow * 128 + ((((ln >> 3) & 1) ^ (ln & 7)) << 4);
#define LOAD_WD(f) ldmatrix4t((wda ^ ((((f) >> 1) & 3) * 32)) + ((f) >> 3) * 4096 + ((f) & 1) * 2048, wd[4 * (f)], wd[4 * (f) + 1], wd[4 * (f) + 2], wd[4 * (f) + 3])
    if (!early) {
      if (b < NFFN) mbar_wait(bar_box + (warp >> 1) * 8, 0);
      LOAD_WF(0);
      __syncwarp();
      mbar_arrive_pred(bar_gate, lane0);
    }
    if (b < NFFN) {
      const uint32_t own = base + unit_of(FT_G, warp >> 1) + (warp & 1) * 8192;
      mbar_wait(bar_box + (4 + (warp >> 1)) * 8, 0);
      LOAD_WF(1);
      uint32_t* const ydst = g_ypart + ((size_t)(warp * 16 + tq * 2) * NFFN + b) * 8 + g;
      PROF(8, ct == PT, 31); STAMP(10);
      bool wdok;
      {
        uint32_t n = 0;
        while (!(wdok = __all_sync(0xffffffffu, mbar_test(bar_box + (8 + (warp >> 1)) * 8, 0))) && !__all_sync(0xffffffffu, mbar_test(bar_sel, 0))) watchdog(n);
      }
      if (wdok) {
#pragma unroll
        for (int f = 0; f < 16; f++) LOAD_WD(f);
      }
      STAMP(11);
      mbar_wait(bar_sel, 0);
      PROF(8, ct == PT, 33); STAMP(12);
      float d[8][4];
#pragma unroll
      for (int i = 0; i < 4; i++) { d[i][0] = 0.f; d[i][1] = 0.f; d[i][2] = 0.f; d[i][3] = 0.f; }
#pragma unroll
      for (int ks = 0; ks < 8; ks++) {
        const uint2 hb = lds2(own + 256 + ks * 32 + tq * 8);
#pragma unroll
        for (int mt = 0; mt < 4; mt++) {
          const int r = ks * 16 + mt * 4;
          mma16816(d[mt], wf[r], wf[r + 1], wf[r + 2], wf[r + 3], hb.x, hb.y);
        }
      }
      sts2(own + (tq * 8 + g) * 8, __float_as_uint((tq & 2) ? ((tq & 1) ? d[1][2] : d[1][0]) : ((tq & 1) ? d[0][2] : d[0][0])),
           __float_as_uint((tq & 2) ? ((tq & 1) ? d[3][2] : d[3][0]) : ((tq & 1) ? d[2][2] : d[2][0])));
      bar_sync(1, 256);
      uint32_t ab[4];
      {
        float G = 0.f, U = 0.f;
        uint2 pv[8];
#pragma unroll
        for (int w8 = 0; w8 < 8; w8++) pv[w8] = lds2(base + ln * 8 + ((FT_G >> (w8 >> 1) * 4) & 15) * UNIT + (w8 & 1) * 8192);
#pragma unroll
        for (int w8 = 0; w8 < 8; w8 += 2) {
          G += __uint_as_float(pv[w8].x) + __uint_as_float(pv[w8 + 1].x);
          U += __uint_as_float(pv[w8].y) + __uint_as_float(pv[w8 + 1].y);
        }
        const float act = rbf(silu_f(rbf(G))) * rbf(U);
        const uint32_t pk = pack_bf(act, __shfl_down_sync(0xffffffffu, act, 1));
#pragma unroll
        for (int i = 0; i < 4; i++) ab[i] = __shfl_sync(0xffffffffu, pk, i * 8 + tq * 2);
      }
      if (!wdok) {
        mbar_wait(bar_box + (8 + (warp >> 1)) * 8, 0);
#pragma unroll
        for (int f = 0; f < 16; f++) LOAD_WD(f);
      }
      PROF(8, ct == PT, 34); STAMP(13);
#pragma unroll
      for (int mt = 0; mt < 8; mt++) {
        d[mt][0] = 0.f; d[mt][1] = 0.f; d[mt][2] = 0.f; d[mt][3] = 0.f;
        mma16816(d[mt], wd[mt * 8], wd[mt * 8 + 1], wd[mt * 8 + 2], wd[mt * 8 + 3], ab[0], ab[1]);
        mma16816(d[mt], wd[mt * 8 + 4], wd[mt * 8 + 5], wd[mt * 8 + 6], wd[mt * 8 + 7], ab[2], ab[3]);
      }
#pragma unroll
      for (int i = 0; i < 4; i++) {
        const int m4 = (i >> 1) * 4, e = (i & 1) * 2;
        const float y = (tq & 2) ? ((tq & 1) ? d[m4 + 3][e] : d[m4 + 2][e]) : ((tq & 1) ? d[m4 + 1][e] : d[m4][e]);
        st_relaxed(ydst + (m4 * 2 + (i & 1)) * NFFN * 8, tagf(y, tag));
      }
      PROF(8, ct == PT, 35); STAMP(14);
    }
    mbar_wait(bar_sel, 0);
    mbar_arrive_pred(bar_win, ct == 0);
    const int iwin = lds1(par + PAR_CONST + 60) & 0x7ff;
    const bool cand = (iwin >> 4) == rb * 8 + warp;
    {
      const uint32_t mm0 = __shfl_sync(0xffffffffu, mm, ln & ~1), mm1 = __shfl_sync(0xffffffffu, mm, ln | 1);
      const uint32_t ih0 = __shfl_sync(0xffffffffu, ih, ln & ~1), ih1 = __shfl_sync(0xffffffffu, ih, ln | 1);
      const uint32_t il0 = __shfl_sync(0xffffffffu, il, ln & ~1), il1 = __shfl_sync(0xffffffffu, il, ln | 1);
#pragma unroll 1
      for (int hf = 0; hf < 2; hf++) {
        uint32_t x[16];
#pragma unroll
        for (int i = 0; i < 8; i += 2) ldmatrix4((trow ^ (i << 4)) + hf * 16384, x[2 * i], x[2 * i + 1], x[2 * i + 2], x[2 * i + 3]);
#pragma unroll
        for (int i = 0; i < 8; i++) {
          const uint4 pv = lds4(par + PAR_T2 + (hf * 8 + i) * 64 + tq * 16);
          x[2 * i] = hadd2(x[2 * i], hmul2(pv.z, ln_mod(x[2 * i], mm0, ih0, il0, pv.x, pv.y)));
          x[2 * i + 1] = hadd2(x[2 * i + 1], hmul2(pv.z, ln_mod(x[2 * i + 1], mm1, ih1, il1, pv.x, pv.y)));
        }
#pragma unroll
        for (int i = 0; i < 8; i += 2) stmatrix4((trow ^ (i << 4)) + hf * 16384, x[2 * i], x[2 * i + 1], x[2 * i + 2], x[2 * i + 3]);
      }
      if (!cand) fence_async_smem();
      __syncwarp();
      if (!cand && elect_one()) {
        tma2d_store(&maps.out, res + warp * 2048, cj * 128, rb * 128 + warp * 16);
        tma2d_store(&maps.out, res + 16384 + warp * 2048, cj * 128 + 64, rb * 128 + warp * 16);
        asm volatile("cp.async.bulk.commit_group;" ::: "memory");
      }
    }
    if (cand) {
      const int wrow0 = warp * 16;
#pragma unroll 2
      for (int p = 0; p < 8; p++) {
        const int row = 2 * p + (ln >> 4), ch = ln & 15;
        const uint4 v = lds4(res + (ch >> 3) * 16384 + (wrow0 + row) * 128 + (((ch & 7) ^ (row & 7)) << 4));
        if (rb * 128 + wrow0 + row != iwin) *reinterpret_cast<uint4*>(P.out + (size_t)(rb * 128 + wrow0 + row) * DM + cj * 128 + ch * 8) = v;
      }
    }
    asm volatile("cp.async.bulk.wait_group.read 0;" ::: "memory");
    PROF(8, ct == PT, 11); STAMP(15);
    cluster_wait();
  }
}

typedef CUresult (*EncodeFn)(CUtensorMap*, CUtensorMapDataType, cuuint32_t, void*, const cuuint64_t*, const cuuint64_t*,
                             const cuuint32_t*, const cuuint32_t*, CUtensorMapInterleave, CUtensorMapSwizzle,
                             CUtensorMapL2promotion, CUtensorMapFloatOOBfill);

void map2d(EncodeFn enc, CUtensorMap* m, const void* p, uint64_t rows, uint64_t cols, uint32_t brows) {
  cuuint64_t dims[2] = {cols, rows}, strides[1] = {cols * 2};
  cuuint32_t box[2] = {64, brows}, es[2] = {1, 1};
  enc(m, CU_TENSOR_MAP_DATA_TYPE_BFLOAT16, 2, const_cast<void*>(p), dims, strides, box, es, CU_TENSOR_MAP_INTERLEAVE_NONE,
      CU_TENSOR_MAP_SWIZZLE_128B, CU_TENSOR_MAP_L2_PROMOTION_L2_256B, CU_TENSOR_MAP_FLOAT_OOB_FILL_NONE);
}
void map2d_narrow(EncodeFn enc, CUtensorMap* m, const void* p, uint64_t rows, uint64_t cols, uint32_t brows) {
  cuuint64_t dims[2] = {cols, rows}, strides[1] = {cols * 2};
  cuuint32_t box[2] = {32, brows}, es[2] = {1, 1};
  enc(m, CU_TENSOR_MAP_DATA_TYPE_BFLOAT16, 2, const_cast<void*>(p), dims, strides, box, es, CU_TENSOR_MAP_INTERLEAVE_NONE,
      CU_TENSOR_MAP_SWIZZLE_64B, CU_TENSOR_MAP_L2_PROMOTION_L2_64B, CU_TENSOR_MAP_FLOAT_OOB_FILL_NONE);
}
void map3d(EncodeFn enc, CUtensorMap* m, const void* p, uint64_t rows, uint64_t cols, uint32_t brows, uint32_t nch) {
  cuuint64_t dims[3] = {64, rows, cols / 64}, strides[2] = {cols * 2, 128};
  cuuint32_t box[3] = {64, brows, nch}, es[3] = {1, 1, 1};
  enc(m, CU_TENSOR_MAP_DATA_TYPE_BFLOAT16, 3, const_cast<void*>(p), dims, strides, box, es, CU_TENSOR_MAP_INTERLEAVE_NONE,
      CU_TENSOR_MAP_SWIZZLE_128B, CU_TENSOR_MAP_L2_PROMOTION_L2_256B, CU_TENSOR_MAP_FLOAT_OOB_FILL_NONE);
}

}

extern "C" void kernel_launch(void* const* d_in, const int* in_sizes, int n_in, void* d_out, int out_size) {
  (void)in_sizes; (void)n_in; (void)out_size;
  static EncodeFn enc = nullptr;
  if (!enc) {
    void* fn = nullptr;
    cudaDriverEntryPointQueryResult st;
    cudaGetDriverEntryPoint("cuTensorMapEncodeTiled", &fn, cudaEnableDefault, &st);
    enc = (EncodeFn)fn;
    cudaFuncSetAttribute(fused_kernel, cudaFuncAttributeMaxDynamicSharedMemorySize, SMEM_BYTES);
  }
  Maps maps;
  map2d(enc, &maps.x, d_in[0], SEQ, DM, 128);
  map2d(enc, &maps.out, d_out, SEQ, DM, 16);
  map3d(enc, &maps.wq, d_in[3], DM, NQ, 64, 2);
  map3d(enc, &maps.k, d_in[1], 4 * SK, 128, 128, 1);
  map3d(enc, &maps.v, d_in[2], 4 * SK, 128, 128, 1);
  map3d(enc, &maps.wo, d_in[4], NQ, DM, 64, 2);
  map2d_narrow(enc, &maps.wg, d_in[7], DM, FF, 256);
  map2d_narrow(enc, &maps.wu, d_in[8], DM, FF, 256);
  map3d(enc, &maps.wd, d_in[9], FF, DM, 32, 4);
  map2d_narrow(enc, &maps.wm, d_in[11], DM, NMOD, 256);
  Ptrs p;
  p.x = (const __nv_bfloat16*)d_in[0];
  p.w_r = (const __nv_bfloat16*)d_in[6];
  p.w_gate = (const __nv_bfloat16*)d_in[7];
  p.w_up = (const __nv_bfloat16*)d_in[8];
  p.w_down = (const __nv_bfloat16*)d_in[9];
  p.c = (const __nv_bfloat16*)d_in[10];
  p.w_mod = (const __nv_bfloat16*)d_in[11];
  p.out = (__nv_bfloat16*)d_out;
  fused_kernel<<<NMAIN + NHELP, 384, SMEM_BYTES>>>(maps, p);
}
```

```cpp
#include <cuda_runtime.h>
#include <cuda_bf16.h>
#include <cuda.h>
#include <stdint.h>
#include <type_traits>

#define HD 2
#define HDX 2
#define NRS 8
#define FPACE 3
#define GOST 20
#define WB 2
#define WN 20
#define RES0 17
#define RES1 20
#define HU 32
#define NS1 5
#define PG0 15
#define PSL 0
#define FB0 0
#define FB2 8
#define OPS 8192
#define OFL 0
#define ODS 8
#define MODUL hfma2
#define ODS1 5
#define LD1 0
#define LD2 4
#define FB1 2
#define FPB 8
#define FPACE0 2
#define VREL 5
#define E0 3

namespace {

constexpr int SEQ = 2048, DM = 1024, NQ = 4096, SK = 2048, WIN = 512, FF = 3584, NMOD = 6144;
constexpr int NMAIN = 128, NHELP = 4, NFFN = 112;
constexpr int NSLOT = 4, SLOT_BYTES = 32768, UNIT = 16384, GST_BYTES = 3 * UNIT;
constexpr uint32_t XT1 = 0xDCBA, XT2 = 0x9687;
constexpr uint32_t WT0 = 0xA741, WT1 = 0x7420, WT2 = 0x4A20;
constexpr uint32_t AT0 = WT1, AT1 = WT2;
constexpr uint32_t QT = 0xDC9696DC;
constexpr int OFF_STAGE = 12 * UNIT;
constexpr uint32_t FT_G = 0x07B3, FT_U = 0xA628, FT_D = 0x5149;
constexpr int OFF_RES = 12 * UNIT;
constexpr int OFF_PAR = 14 * UNIT;
constexpr int OFF_BAR = OFF_PAR + 2528;
constexpr int SMEM_BYTES = OFF_BAR + 544;
static_assert(SMEM_BYTES <= 232448, "smem");

constexpr int PAR_T1 = 0;
constexpr int PAR_T2 = 512;
constexpr int PAR_CONST = 1536;
constexpr int PAR_RED = 1600;
constexpr int PAR_SINK = 2176;

struct Maps {
  CUtensorMap x, wq, k, v, wo, wg, wu, wd, wm, out;
};
struct Ptrs {
  const __nv_bfloat16 *x, *w_r, *c, *w_mod, *w_gate, *w_up, *w_down;
  __nv_bfloat16* out;
};

__device__ __align__(1024) uint8_t g_act[16 * 80 * UNIT];
__device__ __align__(128) uint32_t g_mod[NMOD];
__device__ __align__(128) uint32_t g_modp[2 * 2 * DM];
__device__ __align__(128) uint32_t g_ln1[SEQ * 4];
__device__ __align__(128) uint32_t g_cnt_h[16 * 32];
__device__ __align__(128) uint32_t g_cnt_o[128 * 32];
__device__ __align__(128) uint32_t g_xch[NMAIN * 8 * 256 * 4];
__device__ __align__(128) uint32_t g_stats[8 * SEQ * 4];
__device__ __align__(128) uint32_t g_cand[32];
__device__ __align__(128) uint32_t g_row[16 * 2 * DM];
__device__ __align__(128) uint32_t g_ypart[NMAIN * NFFN * 8];
__device__ uint32_t g_epoch;

__device__ __forceinline__ uint32_t fresh_lane() { uint32_t l; asm volatile("mov.u32 %0, %%laneid;" : "=r"(l)); return l; }
__device__ __forceinline__ uint32_t frag_offset(int warp) {
  const uint32_t l = fresh_lane();
  return ((warp & 3) * 16 + (l & 15)) * 128 + (((l >> 4) ^ (l & 7)) << 4);
}
__device__ __forceinline__ bool elect_one() {
  uint32_t p;
  asm volatile("{ .reg .pred q; elect.sync _|q, 0xffffffff; selp.u32 %0, 1, 0, q; }" : "=r"(p));
  return p;
}
__device__ __forceinline__ uint32_t smem_u32(const void* p) { return (uint32_t)__cvta_generic_to_shared(p); }
__device__ __forceinline__ void mbar_init(uint32_t bar, uint32_t cnt) {
  asm volatile("mbarrier.init.shared::cta.b64 [%0], %1;" ::"r"(bar), "r"(cnt) : "memory");
}
__device__ __forceinline__ void mbar_expect_tx(uint32_t bar, uint32_t bytes) {
  asm volatile("mbarrier.arrive.expect_tx.shared::cta.b64 _, [%0], %1;" ::"r"(bar), "r"(bytes) : "memory");
}
__device__ __forceinline__ void mbar_arrive(uint32_t bar) {
  asm volatile("mbarrier.arrive.shared::cta.b64 _, [%0];" ::"r"(bar) : "memory");
}
__device__ __forceinline__ void mbar_arrive_pred(uint32_t bar, bool p) {
  asm volatile("{ .reg .pred p; setp.ne.b32 p, %1, 0; @p mbarrier.arrive.shared::cta.b64 _, [%0]; }" ::"r"(bar), "r"((int)p) : "memory");
}
__device__ __forceinline__ void mbar_arrive_cl(uint32_t bar, uint32_t off, bool p = true) {
  asm volatile("{ .reg .pred p, q; .reg .b32 a; setp.ne.b32 q, %2, 0; setp.ne.and.b32 p, %0, 0, q; add.u32 a, %0, %1; @p mbarrier.arrive.shared::cluster.b64 _, [a]; }"
               ::"r"(bar), "r"(off), "r"((int)p) : "memory");
}
__device__ __forceinline__ uint32_t mapa(uint32_t addr, uint32_t cta) {
  uint32_t r; asm("mapa.shared::cluster.u32 %0, %1, %2;" : "=r"(r) : "r"(addr), "r"(cta)); return r;
}
__device__ __forceinline__ void cluster_arrive() { asm volatile("barrier.cluster.arrive.relaxed.aligned;" ::: "memory"); }
__device__ __forceinline__ void cluster_wait() { asm volatile("barrier.cluster.wait.aligned;" ::: "memory"); }
__device__ __forceinline__ void watchdog(uint32_t& n) {
}
__device__ __forceinline__ void mbar_wait(uint32_t bar, uint32_t parity) {
  asm volatile("{\n.reg .pred p;\nWAIT_%=:\nmbarrier.try_wait.parity.shared::cta.b64 p, [%0], %1;\n@!p bra WAIT_%=;\n}" ::"r"(bar), "r"(parity) : "memory");
}
__device__ __forceinline__ bool mbar_test(uint32_t bar, uint32_t parity) {
  uint32_t ok;
  asm volatile("{\n.reg .pred p;\nmbarrier.test_wait.parity.shared::cta.b64 p, [%1], %2;\nselp.u32 %0, 1, 0, p;\n}" : "=r"(ok) : "r"(bar), "r"(parity) : "memory");
  return ok;
}
__device__ __forceinline__ uint64_t l2_stream() {
  uint64_t f; asm("createpolicy.fractional.L2::evict_first.b64 %0, 1.0;" : "=l"(f)); return f;
}
__device__ __forceinline__ void tma2d(uint32_t dst, const CUtensorMap* m, int c0, int c1, uint32_t bar) {
  asm volatile("cp.async.bulk.tensor.2d.shared::cluster.global.mbarrier::complete_tx::bytes.L2::cache_hint [%0], [%1, {%3, %4}], [%2], %5;"
               ::"r"(dst), "l"(m), "r"(bar), "r"(c0), "r"(c1), "l"(l2_stream()) : "memory");
}
__device__ __forceinline__ void bulk_load(uint32_t dst, const void* src, uint32_t bytes, uint32_t bar) {
  asm volatile("cp.async.bulk.shared::cluster.global.mbarrier::complete_tx::bytes [%0], [%1], %2, [%3];" ::"r"(dst), "l"(src), "r"(bytes), "r"(bar) : "memory");
}
__device__ __forceinline__ void bulk_load_stream(uint32_t dst, const void* src, uint32_t bytes, uint32_t bar) {
  asm volatile("cp.async.bulk.shared::cluster.global.mbarrier::complete_tx::bytes.L2::cache_hint [%0], [%1], %2, [%3], %4;"
               ::"r"(dst), "l"(src), "r"(bytes), "r"(bar), "l"(l2_stream()) : "memory");
}
__device__ __forceinline__ void tma2d_store(const CUtensorMap* m, uint32_t src, int c0, int c1) {
  asm volatile("cp.async.bulk.tensor.2d.global.shared::cta.bulk_group [%0, {%2, %3}], [%1];" ::"l"(m), "r"(src), "r"(c0), "r"(c1) : "memory");
}
__device__ __forceinline__ void bulk_store(void* dst, uint32_t src, uint32_t bytes) {
  asm volatile("cp.async.bulk.global.shared::cta.bulk_group [%0], [%1], %2;" ::"l"(dst), "r"(src), "r"(bytes) : "memory");
}
__device__ __forceinline__ uint32_t unit_of(uint32_t table, uint32_t i) { return ((table >> (i * 4)) & 15) * UNIT; }
__device__ __forceinline__ void tma3d(uint32_t dst, const CUtensorMap* m, int c0, int c1, int c2, uint32_t bar) {
  asm volatile("cp.async.bulk.tensor.3d.shared::cluster.global.mbarrier::complete_tx::bytes.L2::cache_hint [%0], [%1, {%3, %4, %5}], [%2], %6;"
               ::"r"(dst), "l"(m), "r"(bar), "r"(c0), "r"(c1), "r"(c2), "l"(l2_stream()) : "memory");
}
template <bool STREAM>
__device__ __forceinline__ void tma3d_mc(uint32_t dst, const CUtensorMap* m, int c0, int c1, int c2, uint32_t bar) {
  if (STREAM)
    asm volatile("cp.async.bulk.tensor.3d.shared::cluster.global.mbarrier::complete_tx::bytes.multicast::cluster.L2::cache_hint [%0], [%1, {%3, %4, %5}], [%2], %6, %7;"
                 ::"r"(dst), "l"(m), "r"(bar), "r"(c0), "r"(c1), "r"(c2), "h"((uint16_t)3), "l"(l2_stream()) : "memory");
  else
    asm volatile("cp.async.bulk.tensor.3d.shared::cluster.global.mbarrier::complete_tx::bytes.multicast::cluster [%0], [%1, {%3, %4, %5}], [%2], %6;"
                 ::"r"(dst), "l"(m), "r"(bar), "r"(c0), "r"(c1), "r"(c2), "h"((uint16_t)3) : "memory");
}
__device__ __forceinline__ void prefetch_map(const CUtensorMap* m) {
  asm volatile("prefetch.tensormap [%0];" ::"l"(m) : "memory");
}
__device__ __forceinline__ void fence_async() { asm volatile("fence.proxy.async.global;" ::: "memory"); }
__device__ __forceinline__ void fence_async_smem() { asm volatile("fence.proxy.async.shared::cta;" ::: "memory"); }
__device__ __forceinline__ void bar_sync(int id, int n) { asm volatile("bar.sync %0, %1;" ::"r"(id), "r"(n) : "memory"); }
__device__ __forceinline__ void bar_arrive(int id, int n) { asm volatile("bar.arrive %0, %1;" ::"r"(id), "r"(n) : "memory"); }
__device__ __forceinline__ void wg_fence() { asm volatile("wgmma.fence.sync.aligned;" ::: "memory"); }
__device__ __forceinline__ void wg_commit() { asm volatile("wgmma.commit_group.sync.aligned;" ::: "memory"); }
template <int N> __device__ __forceinline__ void wg_wait() { asm volatile("wgmma.wait_group.sync.aligned %0;" ::"n"(N) : "memory"); }
__device__ __forceinline__ uint64_t make_desc(uint32_t addr, uint32_t lbo, uint32_t sbo) {
  return (uint64_t)((addr & 0x3FFFF) >> 4) | ((uint64_t)(lbo >> 4) << 16) | ((uint64_t)(sbo >> 4) << 32) | (1ull << 62);
}
__device__ __forceinline__ uint32_t ld_relaxed(const uint32_t* p) {
  uint32_t v; asm volatile("ld.relaxed.gpu.global.u32 %0, [%1];" : "=r"(v) : "l"(p) : "memory"); return v;
}
__device__ __forceinline__ uint32_t ld_acquire(const uint32_t* p) {
  uint32_t v; asm volatile("ld.acquire.gpu.global.u32 %0, [%1];" : "=r"(v) : "l"(p) : "memory"); return v;
}
__device__ __forceinline__ uint4 ld_relaxed4(const uint32_t* p) {
  uint4 v; asm volatile("ld.relaxed.gpu.global.v4.u32 {%0,%1,%2,%3}, [%4];" : "=r"(v.x), "=r"(v.y), "=r"(v.z), "=r"(v.w) : "l"(p) : "memory"); return v;
}
__device__ __forceinline__ uint2 ld_relaxed2(const uint32_t* p) {
  uint2 v; asm volatile("ld.relaxed.gpu.global.v2.u32 {%0,%1}, [%2];" : "=r"(v.x), "=r"(v.y) : "l"(p) : "memory"); return v;
}
__device__ __forceinline__ void st_relaxed(uint32_t* p, uint32_t v) {
  asm volatile("st.relaxed.gpu.global.u32 [%0], %1;" ::"l"(p), "r"(v) : "memory");
}
__device__ __forceinline__ void st_relaxed2(uint32_t* p, uint32_t a, uint32_t b) {
  asm volatile("st.relaxed.gpu.global.v2.u32 [%0], {%1,%2};" ::"l"(p), "r"(a), "r"(b) : "memory");
}
__device__ __forceinline__ void st_relaxed4(uint32_t* p, uint32_t a, uint32_t b, uint32_t c, uint32_t d) {
  asm volatile("st.relaxed.gpu.global.v4.u32 [%0], {%1,%2,%3,%4};" ::"l"(p), "r"(a), "r"(b), "r"(c), "r"(d) : "memory");
}
__device__ __forceinline__ void st_b128(uint32_t* p, uint32_t a, uint32_t b, uint32_t c, uint32_t d) {
  asm volatile("{ .reg .b64 u, v; .reg .b128 w; mov.b64 u, {%1, %2}; mov.b64 v, {%3, %4}; mov.b128 w, {u, v}; st.relaxed.gpu.global.b128 [%0], w; }"
               ::"l"(p), "r"(a), "r"(b), "r"(c), "r"(d) : "memory");
}
__device__ __forceinline__ uint4 ld_b128(const uint32_t* p) {
  uint4 r;
  asm volatile("{ .reg .b64 u, v; .reg .b128 w; ld.relaxed.gpu.global.b128 w, [%4]; mov.b128 {u, v}, w; mov.b64 {%0, %1}, u; mov.b64 {%2, %3}, v; }"
               : "=r"(r.x), "=r"(r.y), "=r"(r.z), "=r"(r.w) : "l"(p) : "memory");
  return r;
}
__device__ __forceinline__ void st_pairs(uint32_t* p, uint32_t a, uint32_t b, uint32_t tag) {
  asm volatile("{ .reg .b64 u, v; mov.b64 u, {%1, %3}; mov.b64 v, {%2, %3}; st.relaxed.gpu.global.v2.b64 [%0], {u, v}; }"
               ::"l"(p), "r"(a), "r"(b), "r"(tag) : "memory");
}
__device__ __forceinline__ uint4 ld_pairs(const uint32_t* p) {
  uint4 v;
  asm volatile("{ .reg .b64 u, v; ld.relaxed.gpu.global.v2.b64 {u, v}, [%4]; mov.b64 {%0, %1}, u; mov.b64 {%2, %3}, v; }"
               : "=r"(v.x), "=r"(v.y), "=r"(v.z), "=r"(v.w) : "l"(p) : "memory");
  return v;
}
__device__ __forceinline__ uint2 ld_pair(const uint32_t* p) {
  uint2 v;
  asm volatile("{ .reg .b64 u; ld.relaxed.gpu.global.b64 u, [%2]; mov.b64 {%0, %1}, u; }" : "=r"(v.x), "=r"(v.y) : "l"(p) : "memory");
  return v;
}
__device__ __forceinline__ void red_release(uint32_t* p, uint32_t v) {
  asm volatile("red.release.gpu.global.add.u32 [%0], %1;" ::"l"(p), "r"(v) : "memory");
}
__device__ __forceinline__ uint32_t ldg_nc1(const void* p) {
  uint32_t v;
  asm volatile("ld.global.nc.u32 %0, [%1];" : "=r"(v) : "l"(p));
  return v;
}
__device__ __forceinline__ uint4 ldg_nc4(const void* p) {
  uint4 v; asm volatile("ld.global.nc.L1::no_allocate.v4.u32 {%0,%1,%2,%3}, [%4];" : "=r"(v.x), "=r"(v.y), "=r"(v.z), "=r"(v.w) : "l"(p)); return v;
}
__device__ __forceinline__ uint4 ldg_stream4(const void* p) {
  uint4 v;
  asm volatile("ld.global.nc.L1::no_allocate.L2::cache_hint.v4.u32 {%0,%1,%2,%3}, [%4], %5;" : "=r"(v.x), "=r"(v.y), "=r"(v.z), "=r"(v.w) : "l"(p), "l"(l2_stream()));
  return v;
}
__device__ __forceinline__ void stg4(void* p, uint4 v) {
  asm volatile("st.global.v4.u32 [%0], {%1,%2,%3,%4};" ::"l"(p), "r"(v.x), "r"(v.y), "r"(v.z), "r"(v.w) : "memory");
}
__device__ __forceinline__ void wait_counter(const uint32_t* p, uint32_t target) {
  uint32_t n = 0;
  while (__any_sync(0xffffffffu, (int)(ld_acquire(p) - target) < 0)) { watchdog(n); }
}
__device__ __forceinline__ uint32_t tagf(float v, uint32_t tag) { return (__float_as_uint(v) & ~3u) | tag; }
__device__ __forceinline__ bool tag_ok(uint4 v, uint32_t tag) { return (((v.x ^ tag) | (v.y ^ tag) | (v.z ^ tag) | (v.w ^ tag)) & 3u) == 0; }
__device__ __forceinline__ float untag_sum(uint32_t a, uint32_t b) { return __uint_as_float(a & ~3u) + __uint_as_float(b & ~3u); }
__device__ __forceinline__ uint4 poll4(const uint32_t* p, uint32_t tag) {
  uint4 v = ld_relaxed4(p);
  uint32_t n = 0;
  while (!__all_sync(0xffffffffu, tag_ok(v, tag))) { v = ld_relaxed4(p); watchdog(n); }
  return v;
}
__device__ __forceinline__ float bf_lo(uint32_t v) { return __uint_as_float(v << 16); }
__device__ __forceinline__ float bf_hi(uint32_t v) { return __uint_as_float(v & 0xffff0000u); }
__device__ __forceinline__ uint32_t pack_bf(float lo, float hi) {
  uint32_t r; asm("cvt.rn.bf16x2.f32 %0, %1, %2;" : "=r"(r) : "f"(hi), "f"(lo)); return r;
}
__device__ __forceinline__ float rbf(float v) { return __uint_as_float(pack_bf(0.f, v) & 0xffff0000u); }
__device__ __forceinline__ uint32_t hmul2(uint32_t a, uint32_t b) {
  uint32_t r; asm("mul.rn.bf16x2 %0, %1, %2;" : "=r"(r) : "r"(a), "r"(b)); return r;
}
__device__ __forceinline__ uint32_t hadd2(uint32_t a, uint32_t b) {
  uint32_t r; asm("add.rn.bf16x2 %0, %1, %2;" : "=r"(r) : "r"(a), "r"(b)); return r;
}
__device__ __forceinline__ uint32_t hsub2(uint32_t a, uint32_t b) {
  uint32_t r; asm("sub.rn.bf16x2 %0, %1, %2;" : "=r"(r) : "r"(a), "r"(b)); return r;
}
__device__ __forceinline__ uint32_t hmax2(uint32_t a, uint32_t b) {
  uint32_t r; asm("max.bf16x2 %0, %1, %2;" : "=r"(r) : "r"(a), "r"(b)); return r;
}
__device__ __forceinline__ float rcp(float x) { float r; asm("rcp.approx.ftz.f32 %0, %1;" : "=f"(r) : "f"(x)); return r; }
__device__ __forceinline__ float ex2(float x) { float r; asm("ex2.approx.ftz.f32 %0, %1;" : "=f"(r) : "f"(x)); return r; }
__device__ __forceinline__ void stmatrix4(uint32_t addr, uint32_t a, uint32_t b, uint32_t c, uint32_t d) {
  asm volatile("stmatrix.sync.aligned.m8n8.x4.shared.b16 [%0], {%1,%2,%3,%4};" ::"r"(addr), "r"(a), "r"(b), "r"(c), "r"(d) : "memory");
}
__device__ __forceinline__ void ldmatrix4(uint32_t addr, uint32_t& a, uint32_t& b, uint32_t& c, uint32_t& d) {
  asm volatile("ldmatrix.sync.aligned.m8n8.x4.shared.b16 {%0,%1,%2,%3}, [%4];" : "=r"(a), "=r"(b), "=r"(c), "=r"(d) : "r"(addr) : "memory");
}
__device__ __forceinline__ void ldmatrix4t(uint32_t addr, uint32_t& a, uint32_t& b, uint32_t& c, uint32_t& d) {
  asm volatile("ldmatrix.sync.aligned.m8n8.x4.trans.shared.b16 {%0,%1,%2,%3}, [%4];" : "=r"(a), "=r"(b), "=r"(c), "=r"(d) : "r"(addr) : "memory");
}
__device__ __forceinline__ void mma16816(float (&d)[4], uint32_t a0, uint32_t a1, uint32_t a2, uint32_t a3, uint32_t b0, uint32_t b1) {
  asm volatile("mma.sync.aligned.m16n8k16.row.col.f32.bf16.bf16.f32 {%0,%1,%2,%3}, {%4,%5,%6,%7}, {%8,%9}, {%0,%1,%2,%3};"
               : "+f"(d[0]), "+f"(d[1]), "+f"(d[2]), "+f"(d[3]) : "r"(a0), "r"(a1), "r"(a2), "r"(a3), "r"(b0), "r"(b1));
}
__device__ __forceinline__ void sts1(uint32_t a, uint32_t v) { asm volatile("st.shared.u32 [%0], %1;" ::"r"(a), "r"(v) : "memory"); }
__device__ __forceinline__ uint4 lds4(uint32_t a) {
  uint4 v; asm volatile("ld.shared.v4.u32 {%0,%1,%2,%3}, [%4];" : "=r"(v.x), "=r"(v.y), "=r"(v.z), "=r"(v.w) : "r"(a) : "memory"); return v;
}
__device__ __forceinline__ uint2 lds2(uint32_t a) {
  uint2 v; asm volatile("ld.shared.v2.u32 {%0,%1}, [%2];" : "=r"(v.x), "=r"(v.y) : "r"(a) : "memory"); return v;
}
__device__ __forceinline__ uint32_t lds1(uint32_t a) {
  uint32_t v; asm volatile("ld.shared.u32 %0, [%1];" : "=r"(v) : "r"(a) : "memory"); return v;
}
__device__ __forceinline__ void sts2(uint32_t a, uint32_t x, uint32_t y) { asm volatile("st.shared.v2.u32 [%0], {%1,%2};" ::"r"(a), "r"(x), "r"(y) : "memory"); }
__device__ __forceinline__ void sts4(uint32_t a, uint4 v) {
  asm volatile("st.shared.v4.u32 [%0], {%1,%2,%3,%4};" ::"r"(a), "r"(v.x), "r"(v.y), "r"(v.z), "r"(v.w) : "memory");
}
__device__ __forceinline__ float silu_f(float v) { return __fdividef(v, 1.f + __expf(-v)); }
__device__ __forceinline__ uint32_t hfma2(uint32_t a, uint32_t b, uint32_t c) {
  uint32_t r; asm("fma.rn.bf16x2 %0, %1, %2, %3;" : "=r"(r) : "r"(a), "r"(b), "r"(c)); return r;
}
__device__ __forceinline__ void split_inv(float sd, uint32_t& ih, uint32_t& il) {
  const float inv = rcp(sd);
  ih = pack_bf(inv, inv);
  const float lo = inv - bf_lo(ih);
  il = pack_bf(lo, lo);
}
__device__ __forceinline__ uint32_t ln_norm(uint32_t x, uint32_t mean2, uint32_t ih, uint32_t il) {
  const uint32_t d = hsub2(x, mean2);
  return hfma2(d, ih, hmul2(d, il));
}
__device__ __forceinline__ uint32_t modul(uint32_t n, uint32_t c1, uint32_t sh) { return hadd2(hmul2(n, c1), sh); }
__device__ __forceinline__ uint32_t ln_mod(uint32_t x, uint32_t mean2, uint32_t ih, uint32_t il, uint32_t c1, uint32_t sh) {
  return modul(ln_norm(x, mean2, ih, il), c1, sh);
}

#define R8(a, i) "+f"(a[i]), "+f"(a[i + 1]), "+f"(a[i + 2]), "+f"(a[i + 3]), "+f"(a[i + 4]), "+f"(a[i + 5]), "+f"(a[i + 6]), "+f"(a[i + 7])
#define D64 "{%0,%1,%2,%3,%4,%5,%6,%7,%8,%9,%10,%11,%12,%13,%14,%15,%16,%17,%18,%19,%20,%21,%22,%23,%24,%25,%26,%27,%28,%29,%30,%31," \
            "%32,%33,%34,%35,%36,%37,%38,%39,%40,%41,%42,%43,%44,%45,%46,%47,%48,%49,%50,%51,%52,%53,%54,%55,%56,%57,%58,%59,%60,%61,%62,%63}"
template <int TB>
__device__ __forceinline__ void mma_ss(float (&d)[64], uint64_t da, uint64_t db, int sc) {
  asm volatile("{\n.reg .pred p;\nsetp.ne.b32 p, %66, 0;\n"
               "wgmma.mma_async.sync.aligned.m64n128k16.f32.bf16.bf16 " D64 ", %64, %65, p, 1, 1, 0, %67;\n}"
               : R8(d, 0), R8(d, 8), R8(d, 16), R8(d, 24), R8(d, 32), R8(d, 40), R8(d, 48), R8(d, 56)
               : "l"(da), "l"(db), "r"(sc), "n"(TB));
}
template <int TB>
__device__ __forceinline__ void mma_rs(float (&d)[64], uint32_t a0, uint32_t a1, uint32_t a2, uint32_t a3, uint64_t db, int sc) {
  asm volatile("{\n.reg .pred p;\nsetp.ne.b32 p, %69, 0;\n"
               "wgmma.mma_async.sync.aligned.m64n128k16.f32.bf16.bf16 " D64 ", {%64,%65,%66,%67}, %68, p, 1, 1, %70;\n}"
               : R8(d, 0), R8(d, 8), R8(d, 16), R8(d, 24), R8(d, 32), R8(d, 40), R8(d, 48), R8(d, 56)
               : "r"(a0), "r"(a1), "r"(a2), "r"(a3), "l"(db), "r"(sc), "n"(TB));
}
#define D128 "{%0,%1,%2,%3,%4,%5,%6,%7,%8,%9,%10,%11,%12,%13,%14,%15,%16,%17,%18,%19,%20,%21,%22,%23,%24,%25,%26,%27,%28,%29,%30,%31," \
             "%32,%33,%34,%35,%36,%37,%38,%39,%40,%41,%42,%43,%44,%45,%46,%47,%48,%49,%50,%51,%52,%53,%54,%55,%56,%57,%58,%59,%60,%61,%62,%63," \
             "%64,%65,%66,%67,%68,%69,%70,%71,%72,%73,%74,%75,%76,%77,%78,%79,%80,%81,%82,%83,%84,%85,%86,%87,%88,%89,%90,%91,%92,%93,%94,%95," \
             "%96,%97,%98,%99,%100,%101,%102,%103,%104,%105,%106,%107,%108,%109,%110,%111,%112,%113,%114,%115,%116,%117,%118,%119,%120,%121,%122,%123,%124,%125,%126,%127}"
#define R128(d, e) R8(d, 0), R8(d, 8), R8(d, 16), R8(d, 24), R8(d, 32), R8(d, 40), R8(d, 48), R8(d, 56), \
                   R8(e, 0), R8(e, 8), R8(e, 16), R8(e, 24), R8(e, 32), R8(e, 40), R8(e, 48), R8(e, 56)
__device__ __forceinline__ void mma256_ss(float (&d)[64], float (&e)[64], uint64_t da, uint64_t db, int sc) {
  asm volatile("{\n.reg .pred p;\nsetp.ne.b32 p, %130, 0;\n"
               "wgmma.mma_async.sync.aligned.m64n256k16.f32.bf16.bf16 " D128 ", %128, %129, p, 1, 1, 0, 1;\n}"
               : R128(d, e) : "l"(da), "l"(db), "r"(sc));
}
__device__ __forceinline__ void mma256_rs(float (&d)[64], float (&e)[64], uint32_t a0, uint32_t a1, uint32_t a2, uint32_t a3, uint64_t db) {
  asm volatile("{\n.reg .pred p;\nsetp.ne.b32 p, 1, 0;\n"
               "wgmma.mma_async.sync.aligned.m64n256k16.f32.bf16.bf16 " D128 ", {%128,%129,%130,%131}, %132, p, 1, 1, 1;\n}"
               : R128(d, e) : "r"(a0), "r"(a1), "r"(a2), "r"(a3), "l"(db));
}
template <int N> __device__ __forceinline__ void keep(float (&a)[N]) {
#pragma unroll
  for (int i = 0; i < N; i++) asm volatile("" : "+f"(a[i])::"memory");
}
template <int N> __device__ __forceinline__ void keep(uint32_t (&a)[N]) {
#pragma unroll
  for (int i = 0; i < N; i++) asm volatile("" : "+r"(a[i])::"memory");
}

#define STAMP(idx) do {} while (0)
#define PROF(grp, cond, idx) do {} while (0)

constexpr float SCL2 = 1.4426950408889634f * 0.08838834764831845f;

__device__ __forceinline__ void pack_p(const float (&s)[64], uint32_t (&p)[32]) {
#pragma unroll
  for (int i = 0; i < 32; i++) p[i] = pack_bf(s[2 * i], s[2 * i + 1]);
}

__device__ __forceinline__ void issue_qk(float (&s)[64], uint32_t q0, uint32_t q1, uint32_t kslot) {
  const uint64_t db = make_desc(kslot, 16, 1024), da0 = make_desc(q0, 16, 1024), da1 = make_desc(q1, 16, 1024);
#pragma unroll
  for (int kk = 0; kk < 8; kk++) mma_ss<0>(s, (kk < 4 ? da0 : da1) + (kk & 3) * 2, db + (kk >> 2) * 1024 + (kk & 3) * 2, kk != 0);
}
__device__ __forceinline__ void issue_pv(float (&o)[64], uint32_t (&p)[32], uint32_t vslot, int acc) {
  uint64_t db = make_desc(vslot, 16384, 1024);
#pragma unroll
  for (int kk = 0; kk < 8; kk++)
    mma_rs<1>(o, p[4 * kk], p[4 * kk + 1], p[4 * kk + 2], p[4 * kk + 3], db + kk * 128, kk == 0 ? acc : 1);
}

template <int H>
__device__ __forceinline__ void store_chunk(const float (&a)[64], uint32_t addr) {
#pragma unroll
  for (int i = 8 * H; i < 8 * H + 8; i += 2)
    stmatrix4(addr ^ ((i & 7) << 4), pack_bf(a[4 * i], a[4 * i + 1]), pack_bf(a[4 * i + 2], a[4 * i + 3]),
              pack_bf(a[4 * i + 4], a[4 * i + 5]), pack_bf(a[4 * i + 6], a[4 * i + 7]));
}
template <int H>
__device__ __forceinline__ void store_chunk(const float (&a)[64], float i0, float i1, uint32_t addr) {
#pragma unroll
  for (int i = 8 * H; i < 8 * H + 8; i += 2)
    stmatrix4(addr ^ ((i & 7) << 4), pack_bf(a[4 * i] * i0, a[4 * i + 1] * i0), pack_bf(a[4 * i + 2] * i1, a[4 * i + 3] * i1),
              pack_bf(a[4 * i + 4] * i0, a[4 * i + 5] * i0), pack_bf(a[4 * i + 6] * i1, a[4 * i + 7] * i1));
}
__device__ __forceinline__ float inv_quad_sum(float l) {
  l += __shfl_xor_sync(0xffffffffu, l, 1);
  l += __shfl_xor_sync(0xffffffffu, l, 2);
  return rcp(l);
}

__device__ __forceinline__ void ln_scalars(float mean, float var, float& mb, float& sd) {
  mb = rbf(mean);
  float r; asm("sqrt.approx.ftz.f32 %0, %1;" : "=f"(r) : "f"(rbf(rbf(var) + 1e-5f)));
  sd = rbf(r);
}

__global__ void __cluster_dims__(2, 1, 1) __launch_bounds__(384, 1) fused_kernel(const __grid_constant__ Maps maps, const Ptrs P) {
  extern __shared__ __align__(1024) uint8_t smem_raw[];
  const uint32_t base = smem_u32(smem_raw);
  const int tid = threadIdx.x, lane = tid & 31;
  const int warp = __shfl_sync(0xffffffffu, tid >> 5, 0);
  const int b = blockIdx.x;
  PROF(31, tid == 0, 0);

  if (b >= NMAIN) {
    float* sc = reinterpret_cast<float*>(smem_raw);
    float* red = sc + DM;
    for (int k = tid; k < DM; k += 384) sc[k] = rbf(silu_f(__bfloat162float(P.c[k])));
    __syncthreads();
    if (tid < 256) {
      const int col = 2048 + (b - NMAIN) * 1024 + (tid & 127) * 8, r0 = (tid >> 7) * 512;
      float acc[8];
#pragma unroll
      for (int e = 0; e < 8; e++) acc[e] = 0.f;
#pragma unroll 1
      for (int r = r0; r < r0 + 512; r += HU) {
        uint4 w[HU];
#pragma unroll
        for (int u = 0; u < HU; u++) w[u] = ldg_stream4(P.w_mod + (size_t)(r + u) * NMOD + col);
#pragma unroll
        for (int u = 0; u < HU; u++) {
          float s = sc[r + u];
          acc[0] += s * bf_lo(w[u].x); acc[1] += s * bf_hi(w[u].x); acc[2] += s * bf_lo(w[u].y); acc[3] += s * bf_hi(w[u].y);
          acc[4] += s * bf_lo(w[u].z); acc[5] += s * bf_hi(w[u].z); acc[6] += s * bf_lo(w[u].w); acc[7] += s * bf_hi(w[u].w);
        }
      }
      if (tid >= 128) {
#pragma unroll
        for (int e = 0; e < 8; e++) red[(tid & 127) * 8 + e] = acc[e];
      }
      const uint32_t tag = ld_relaxed(&g_epoch) % 3 + 1;
      bar_sync(1, 256);
      if (tid < 128) {
        uint32_t o[8];
#pragma unroll
        for (int e = 0; e < 8; e++) o[e] = __float_as_uint(rbf(acc[e] + red[tid * 8 + e])) | tag;
        st_relaxed4(g_mod + col, o[0], o[1], o[2], o[3]);
        st_relaxed4(g_mod + col + 4, o[4], o[5], o[6], o[7]);
        const uint4 wr = ldg_nc4(P.w_r + tid * 8);
        const uint32_t wv[4] = {wr.x, wr.y, wr.z, wr.w};
        float dsum = 0.f;
#pragma unroll
        for (int e = 0; e < 8; e++) {
          const float m = bf_hi(o[e]);
          dsum += (b == NMAIN + 2 ? rbf(1.f + m) : m) * ((e & 1) ? bf_hi(wv[e >> 1]) : bf_lo(wv[e >> 1]));
        }
#pragma unroll
        for (int k = 16; k > 0; k >>= 1) dsum += __shfl_xor_sync(0xffffffffu, dsum, k);
        if (lane == 0) st_relaxed(g_mod + (b - NMAIN) * 4 + warp, tagf(dsum, tag));
      }
    }
    PROF(2, tid == 0, 1);
    return;
  }

  const int rank = b & 1;
  const int rb = ((b >> 4) << 1) | rank, cj = (b >> 1) & 7;
  const uint32_t bfull = base + OFF_BAR, bempty = bfull + NSLOT * 8;
  const uint32_t gfull = bempty + NSLOT * 8, gempty = gfull + 32;
  const uint32_t bar_ofull = gempty + 32;
  const uint32_t bar_ofree = bar_ofull + 32;
  const uint32_t bar_par = bar_ofree + 32;
  const uint32_t bar_mod = bar_par + 8;
  const uint32_t bar_pread = bar_mod + 8;
  const uint32_t bar_xres = bar_pread + 8;
  const uint32_t bar_ring = bar_xres + 8;
  const uint32_t bar_box = bar_ring + 24;
  const uint32_t bar_go = bar_box + 96;
  const uint32_t bar_go2 = bar_go + 16;
  const uint32_t bar_cnt = bar_go + 24;
  const uint32_t xfull = bar_go + 40, xempty = xfull + 32;
  const uint32_t bar_hw = xempty + 32, bar_hx = bar_hw + 8;
  const uint32_t bar_hpub = bar_hx + 16;
  const uint32_t bar_win = bar_hpub + 16;
  const uint32_t bar_rx = bar_win + 8;
  const uint32_t bar_sel = bar_rx + 8;
  const uint32_t bar_gate = bar_sel + 8;
  const uint32_t bar_rel = bar_gate + 8;
  const uint32_t bar_od = bar_rel + 8;
  const uint32_t bar_res = bar_go + 8;
  const uint32_t stage = base + OFF_STAGE, par = base + OFF_PAR;

  if (warp == 8 && elect_one()) {
    for (int s = 0; s < NSLOT; s++) { mbar_init(bfull + s * 8, 1); mbar_init(bempty + s * 8, 16); }
    for (int s = 0; s < 4; s++) { mbar_init(gfull + s * 8, 1); mbar_init(gempty + s * 8, 16); mbar_init(xfull + s * 8, 1); mbar_init(xempty + s * 8, 8); mbar_init(bar_ofree + s * 8, 1); mbar_init(bar_ofull + s * 8, 128); }
    mbar_init(bar_par, 64); mbar_init(bar_mod, 256); mbar_init(bar_pread, 2); mbar_init(bar_xres, 1);
    mbar_init(bar_ring, 8); mbar_init(bar_ring + 8, 8); mbar_init(bar_ring + 16, 8);
    mbar_init(bar_go, 1); mbar_init(bar_go2, 1); mbar_init(bar_cnt, 1); mbar_init(bar_cnt + 8, 1); mbar_init(bar_hpub, 8); mbar_init(bar_hpub + 8, 8); mbar_init(bar_res, 1); mbar_init(bar_win, 1); mbar_init(bar_rx, 1); mbar_init(bar_sel, 64); mbar_init(bar_gate, 8); mbar_init(bar_rel, 8); mbar_init(bar_od, 1);
    for (int s = 0; s < 12; s++) mbar_init(bar_box + s * 8, 1);
    asm volatile("fence.mbarrier_init.release.cluster;" ::: "memory");
    prefetch_map(&maps.x); prefetch_map(&maps.wq); prefetch_map(&maps.k); prefetch_map(&maps.v);
  }
  if (warp == 9 && elect_one()) {
    mbar_init(bar_hw, 1); mbar_init(bar_hx, 1); mbar_init(bar_hx + 8, 1);
    asm volatile("fence.mbarrier_init.release.cluster;" ::: "memory");
    mbar_expect_tx(bar_hw, 32768);
    mbar_expect_tx(bar_hx, 16384);
    mbar_expect_tx(bar_hx + 8, 16384);
    const __nv_bfloat16* xs = P.x + (size_t)(rb * 128 + cj * 16) * DM;
    bulk_load(base + 2 * GST_BYTES, xs, 16384, bar_hx);
    tma2d(stage, &maps.wm, (b >> 1) * 32, rank * 512, bar_hw);
    tma2d(stage + 16384, &maps.wm, (b >> 1) * 32, rank * 512 + 256, bar_hw);
    bulk_load(base + 3 * GST_BYTES, xs + 8 * DM, 16384, bar_hx + 8);
  }
  cluster_arrive();

  if (warp >= 8) {
    asm volatile("setmaxnreg.dec.sync.aligned.u32 40;");
    if (warp < 10) bar_arrive(1, 320);
    const uint32_t epoch = ld_relaxed(&g_epoch);
    cluster_wait();
    if (warp == 8) {
      const int kvrow = (cj >> 1) * SK + (SK - WIN);
      int wch = cj * 8 + rank * 2;
#pragma unroll 1
      for (int ps = 0; ps < 3; ps++) {
        const CUtensorMap* mw = ps == 2 ? &maps.wo : &maps.wq;
        const uint32_t xt = ps == 1 ? XT1 : XT2, wt = ps == 0 ? WT0 : (ps == 1 ? WT1 : WT2);
        const int nst = ps == 2 ? 32 : 16;
#pragma unroll 1
        for (int i = 0; i < nst; i++) {
          const uint32_t bf = gfull + (i & 3) * 8;
          const int kt = ps == 2 ? (((cj & 1) * 4 + ((i >> 1) & 3)) * 4 + (i >> 3)) * 2 + (i & 1) : (i + (ps ? 0 : b & 14)) & 15;
          const uint32_t wd = base + unit_of(wt, i & 3) + rank * UNIT, xd = base + unit_of(xt, i & 3);
          const uint8_t* xs = g_act + (uint32_t)(rb * 80 + (ps - 1) * 16 + kt) * UNIT;
          if (ps == 0 && i == HD) mbar_wait(bar_mod, 0);
          const bool xfirst = ps && i < 2;
          if (ps == 2 && i == 0) mbar_wait(bar_ofree + 24, 0);
          if (i == 0) fence_async();
          mbar_wait(gempty + (i & 3) * 8, ((i >> 2) & 1) ^ 1);
          if (elect_one()) {
            mbar_expect_tx(bf, ps ? GST_BYTES : 2 * UNIT);
            if (xfirst) bulk_load_stream(xd, xs, UNIT, bf);
          }
          if (ps && i < 4) mbar_wait(bempty + i * 8, 1);
          if (elect_one()) tma3d_mc<true>(wd, mw, 0, (i == 31 ? kt ^ (rank * 32) : kt) * 64, i == 31 ? cj * 2 : wch, bf);
          if (ps) {
            if (i == 16 || i == 24) { mbar_wait(bar_cnt + i - 16, 0); fence_async(); }
            if (i == RES0) mbar_wait(bar_res, 0);
            if (i == 2) mbar_wait(bar_ofree + (ps - 1) * 16, 0);
            if (elect_one()) {
              if (i == 31) bulk_load(xd, xs, UNIT, bf); else if (!xfirst) bulk_load_stream(xd, xs, UNIT, bf);
              mbar_arrive_pred(bar_go, i == GOST - 1);
              if (PG0 < 16) mbar_arrive_pred(bar_go2, ps == 1 && i == PG0);
              mbar_arrive_pred(bar_od, i == (ps == 1 ? ODS1 : ODS));
              if (i == RES0) mbar_expect_tx(bar_xres, 32768);
              if (i == RES0 || i == RES1) tma2d(base + OFF_RES + (i == RES1) * UNIT, &maps.x, cj * 128 + (i == RES1) * 64, rb * 128, bar_xres);
            }
          }
        }
        if (ps == 2) break;
        wch = ps ? ((wch >> 3) ^ rank) * 2 : wch + 4;
#pragma unroll 1
        for (int u = 0; u < 16; u++) {
          const bool isk = (u == 0) || ((u & 1) && u < 15);
          const int blk = (isk ? (u + 1) >> 1 : (u == 15 ? 7 : (u >> 1) - 1)) & 3;
          const uint32_t sl = base + unit_of(ps ? AT1 : AT0, u & 3) + rank * UNIT, bf = bfull + (u & 3) * 8;
          if (u < 4) mbar_wait(gempty + ((u + 1) >> 1) * 8, 1);
          mbar_wait(bempty + (u & 3) * 8, ((u >> 2) & 1) ^ 1);
          if (elect_one()) {
            mbar_arrive_pred(bar_go2, ps && u + 16 == PG0);
            mbar_expect_tx(bf, SLOT_BYTES);
            tma3d_mc<false>(sl, isk ? &maps.k : &maps.v, 0, kvrow + blk * 128, rank, bf);
          }
        }
      }
      if (elect_one()) mbar_expect_tx(bar_rx, UNIT);
      mbar_wait(bar_rel, 0);
      if (elect_one()) {
        bulk_load_stream(base + UNIT, g_act + (uint32_t)(rb * 80 + 16 + 63 - (cj & 1) * 32) * UNIT, UNIT, bar_rx);
      }
      if (b < NFFN) {
#pragma unroll 1
        for (int u = 0; u < 12; u++) {
          const uint32_t dst = base + unit_of(u < 4 ? FT_G : (u < 8 ? FT_U : FT_D), u & 3);
          if (elect_one()) mbar_expect_tx(bar_box + u * 8, UNIT);
          if (u == FB0 || u == FB1 || u == FB2) mbar_wait(bar_ring + (u == FB2 ? 16 : u == FB1 ? 8 : 0), 0);
          const int fp = u < FPB ? FPACE0 : FPACE;
          if (u >= fp) mbar_wait(bar_box + (u - fp) * 8, 0);
          if (elect_one()) {
            if (u < 8) tma2d(dst, u < 4 ? &maps.wg : &maps.wu, b * 32, (u & 3) * 256, bar_box + u * 8);
            else tma3d(dst, &maps.wd, 0, b * 32, (u - 8) * 4, bar_box + u * 8);
          }
        }
      }
    } else if (warp == 9) {
      const uint32_t target = 8 * (epoch + 1);
      uint32_t hmask = 0;
#pragma unroll 1
      for (int i = 0; i < 16; i++) {
        if (i == HDX) mbar_wait(bar_mod, 0);
        const uint32_t need = i == 15 ? 0xffffu : 1u << ((2 * cj + i) & 15);
        if (i >= NRS && (hmask & need) != need) {
          uint32_t n = 0;
          do { hmask = __ballot_sync(0xffffffffu, ld_acquire(&g_cnt_h[rb * 32 + (lane & 15)]) == epoch + 1); watchdog(n); } while ((hmask & need) != need);
          PROF(1, lane == 0 && i == NRS, 26);
          fence_async();
        }
        mbar_wait(xempty + (i & 3) * 8, ((i >> 2) & 1) ^ 1);
        if (elect_one()) {
          mbar_expect_tx(xfull + (i & 3) * 8, UNIT);
          if (i < NRS) tma2d(base + (i & 3) * GST_BYTES, &maps.x, ((2 * cj + i) & 15) * 64, rb * 128, xfull + (i & 3) * 8);
          else bulk_load_stream(base + (i & 3) * GST_BYTES, g_act + (uint32_t)(rb * 80 + ((2 * cj + i) & 15)) * UNIT, UNIT, xfull + (i & 3) * 8);
        }
      }
      prefetch_map(&maps.wo);
#pragma unroll 1
      for (int t = 0; t < 4; t++) {
        if (t & 1) mbar_wait(bar_od, t >> 1);
#pragma unroll 1
        for (int p = 0; p < 32768 / OPS; p++) {
          const uint32_t w = p / (16384 / OPS), c = (p / (8192 / OPS)) & 1, off = w * 8192 + (p % (8192 / OPS)) * OPS;
          mbar_wait(bar_ofull + (t & 1) * 16 + w * 8, t >> 1);
          if (elect_one()) {
            bulk_store(g_act + (uint32_t)(rb * 80 + 16 + (cj * 4 + t) * 2 + c) * UNIT + off, base + unit_of(QT, 2 * t + c) + off, OPS);
            asm volatile("cp.async.bulk.commit_group;" ::: "memory");
            asm volatile("cp.async.bulk.wait_group.read %0;" ::"n"(OFL) : "memory");
          }
        }
        if (elect_one()) {
          asm volatile("cp.async.bulk.wait_group.read 0;" ::: "memory");
          mbar_arrive(t < 3 ? bar_ofree + t * 8 : bar_res);
          asm volatile("cp.async.bulk.wait_group 0;" ::: "memory");
          fence_async();
          red_release(&g_cnt_o[((rb * 4 + t) * 2 + (cj >> 2)) * 32], 2);
        }
        if (t) {
          wait_counter(&g_cnt_o[(rb * 8 + 2 * t + (cj & 1)) * 32], target);
          if (t & 1) wait_counter(&g_cnt_o[(rb * 8 + (t == 1 ? cj & 1 : 7 - (cj & 1))) * 32], target);
          if (elect_one()) mbar_arrive(t == 1 ? bar_ofree + 24 : bar_cnt + t * 8 - 16);
        }
      }
      PROF(2, lane == 0, 27);
      const uint32_t tag = epoch % 3 + 1;
      const uint32_t* inbox = g_cand + (lane & 15);
      mbar_wait(bar_ring + 16, 0);
      uint32_t c0 = ld_relaxed(inbox), n = 0;
#define CAND_STEP(cv)                                                                                        \
      {                                                                                                      \
        const bool valid = (cv & 3u) == tag, all = __all_sync(0xffffffffu, valid);                           \
        const uint32_t best = __reduce_max_sync(0xffffffffu, valid ? cv : 0u);                               \
        const uint32_t blk = __ffs(__ballot_sync(0xffffffffu, cv == best)) - 1;                              \
        if (best) sts2(par + PAR_CONST + 56, best, (blk << 7 | (~best >> 2 & 127)) | (all ? 0x1800 : 0x800)); \
        if (all) break;                                                                                      \
        cv = ld_relaxed(inbox);                                                                              \
      }
      while (true) { CAND_STEP(c0) watchdog(n); }
    } else {
      const int t2 = tid - 320;
      mbar_wait(bar_hpub + (warp & 1) * 8, 0);
      PROF(1, t2 == 0, 24);
#pragma unroll 1
      for (int c = 0; c < 8; c++) {
        const uint32_t off = (warp & 1) * UNIT + c * 2048 + lane * 16;
        uint8_t* dst = g_act + (uint32_t)(rb * 80 + cj * 2) * UNIT + off;
        const uint4 v0 = lds4(stage + off), v1 = lds4(stage + off + 512), v2 = lds4(stage + off + 1024), v3 = lds4(stage + off + 1536);
        stg4(dst, v0); stg4(dst + 512, v1); stg4(dst + 1024, v2); stg4(dst + 1536, v3);
      }
      __syncwarp();
      PROF(1, t2 == 0, 15);
      if (lane == 0) {
        mbar_arrive(bar_pread);
        red_release(&g_cnt_h[rb * 32 + cj * 2 + (warp & 1)], 1);
        PROF(1, t2 == 0, 25);
        prefetch_map(&maps.wg); prefetch_map(&maps.wu); prefetch_map(&maps.wd); prefetch_map(&maps.out);
      }
      __syncwarp();
      if (b < NFFN) {
        mbar_wait(bar_go2, 0);
        const __nv_bfloat16* pg = ((b & 1) ? P.w_up : P.w_gate) + (b >> 1) * 64 + (size_t)t2 * FF;
        const __nv_bfloat16* pd = P.w_down + (size_t)b * 32768 + t2 * 64;
        PROF(2, t2 == 0, 13);
#pragma unroll 1
        for (int i = 0; i < WN; i += WB) {
          uint32_t v[WB];
#pragma unroll
          for (int u = 0; u < WB; u++) {
            const int k = i + u;
            asm volatile("ld.global.cg.L2::128B.u32 %0, [%1];" : "=r"(v[u]) : "l"(k < 16 ? pg + (size_t)k * 64 * FF : pd + (k - 16) * 4096));
          }
#pragma unroll
          for (int u = 1; u < WB; u++) v[0] ^= v[u];
          sts1(par + PAR_SINK + t2 * 4, v[0]);
        }
        PROF(2, t2 == 0, 14);
      }
      const uint32_t tag = epoch % 3 + 1;
      mbar_wait(bar_go, 0);
      bar_sync(4, 64);
      if (warp == 10) {
        const uint32_t* src = g_mod + 2 * DM + cj * 128 + lane * 4;
        const uint2 wr = *reinterpret_cast<const uint2*>(P.w_r + cj * 128 + lane * 4);
        uint4 vga, vsb, vcb, vgb;
        uint32_t n = 0;
        do {
          vga = ld_relaxed4(src); vsb = ld_relaxed4(src + DM); vcb = ld_relaxed4(src + 2 * DM); vgb = ld_relaxed4(src + 3 * DM);
          watchdog(n);
        } while (!__all_sync(0xffffffffu, tag_ok(vga, tag) && tag_ok(vsb, tag) && tag_ok(vcb, tag) && tag_ok(vgb, tag)));
        const float c0 = rbf(1.f + bf_hi(vcb.x)), c1 = rbf(1.f + bf_hi(vcb.y)), c2 = rbf(1.f + bf_hi(vcb.z)), c3 = rbf(1.f + bf_hi(vcb.w));
        const float a0 = c0 * bf_lo(wr.x), a1 = c1 * bf_hi(wr.x), a2 = c2 * bf_lo(wr.y), a3 = c3 * bf_hi(wr.y);
        const uint32_t h0 = pack_bf(a0, a1), h1 = pack_bf(a2, a3);
        const uint32_t t1 = par + PAR_T1 + (lane >> 2) * 64 + (lane & 1) * 32 + (lane & 2) * 2;
        sts1(t1, h0); sts1(t1 + 8, pack_bf(a0 - bf_lo(h0), a1 - bf_hi(h0)));
        sts1(t1 + 16, h1); sts1(t1 + 24, pack_bf(a2 - bf_lo(h1), a3 - bf_hi(h1)));
        const uint32_t tg = par + PAR_SINK + (lane >> 3) * 64 + (lane & 1) * 32 + (lane & 6) * 2;
        sts1(tg, __byte_perm(vga.x, vga.y, 0x7632)); sts1(tg + 16, __byte_perm(vga.z, vga.w, 0x7632));
        sts4(par + PAR_T2 + lane * 32, make_uint4(pack_bf(c0, c1), __byte_perm(vsb.x, vsb.y, 0x7632), __byte_perm(vgb.x, vgb.y, 0x7632), __byte_perm(vga.x, vga.y, 0x7632)));
        sts4(par + PAR_T2 + lane * 32 + 16, make_uint4(pack_bf(c2, c3), __byte_perm(vsb.z, vsb.w, 0x7632), __byte_perm(vgb.z, vgb.w, 0x7632), __byte_perm(vga.z, vga.w, 0x7632)));
      } else {
        const uint4 g = poll4((lane & 2) ? g_mod + 8 - (lane & 1) * 4 : g_mod + 5 * DM + b * 8 + (lane & 1) * 4, tag);
        sts1(par + PAR_CONST + 60, 0);
        if (lane < 2) sts4(par + PAR_CONST + 16 + lane * 16, g);
        else if (lane < 4) sts2(par + PAR_CONST + (lane - 2) * 8, __float_as_uint(untag_sum(g.x, g.y) + untag_sum(g.z, g.w)), epoch);
      }
      __syncwarp();
#pragma unroll 4
      for (int q = 0; q < 32; q++) st_b128(g_xch + ((size_t)b * 8 * 256 + q * 64 + t2) * 4, (epoch & 1) << 16, 0, 0, 0);
      for (int q = 0; q < 2; q++) st_relaxed4(g_stats + ((size_t)cj * SEQ + rb * 128 + q * 64 + t2) * 4, 0, 0, 0, 0);
      if (b < NFFN)
        for (int q = 0; q < 4; q++) st_relaxed4(g_ypart + ((size_t)(q * 32 + (t2 >> 1)) * NFFN + b) * 8 + (t2 & 1) * 4, 0, 0, 0, 0);
      st_relaxed4(g_row + rb * 2 * DM + (t2 >> 5) * DM + cj * 128 + (t2 & 31) * 4, 0, 0, 0, 0);
      __threadfence();
      mbar_arrive(bar_par);
      mbar_wait(bar_gate, 0);
      uint32_t have = 0, n = 0;
      while (true) {
        const uint32_t st = lds1(par + PAR_CONST + 60) >> 7;
        if ((st & 31) != have) {
          const uint32_t* hsrc = g_row + (st & 15) * 2 * DM + t2 * 4;
          uint4 hv[4];
          bool ok = true;
#pragma unroll
          for (int i = 0; i < 4; i++) hv[i] = ld_pairs(hsrc + i * 256);
#pragma unroll
          for (int i = 0; i < 4; i++) {
            sts2(base + ((FT_G >> i * 4) & 15) * UNIT + (warp & 1) * 8192 + 256 + lane * 8, hv[i].x, hv[i].z);
            ok = ok && hv[i].y == tag && hv[i].w == tag;
          }
          have = __all_sync(0xffffffffu, ok) ? st & 31 : 0;
        }
        if ((st ^ have) == 32) break;
        watchdog(n);
      }
      mbar_arrive(bar_sel);
    }
    __syncwarp();
    cluster_arrive();
    {
      const uint32_t tag = epoch % 3 + 1, t3 = tid - 256;
      mbar_wait(bar_win, 0);
      uint2 win = lds2(par + PAR_CONST + 56);
      win.y &= 0x7ff;
      const uint32_t* fsrc = g_row + (win.y >> 7) * 2 * DM + (b >> 1) * 16 + (t3 & 3) * 4 + (b & 1) * 2;
      const uint32_t* ysrc = g_ypart + (size_t)b * NFFN * 8 + min(t3, NFFN - 1) * 4;
      uint2 fh = ld_pair(fsrc), fx = ld_pair(fsrc + DM);
      if (PSL) __nanosleep(PSL);
      uint4 ya = ld_relaxed4(ysrc), yb = ld_relaxed4(ysrc + NFFN * 4);
      const float rwin = __uint_as_float(((int)win.x < 0 ? win.x & 0x7fffffffu : ~win.x) & ~0x1ffu);
      const float rs = rbf(rcp(1.f + __expf(-rbf(rwin))));
      uint32_t n = 0;
      while (__any_sync(0xffffffffu, fh.y != tag || fx.y != tag)) { fh = ld_pair(fsrc); fx = ld_pair(fsrc + DM); watchdog(n); }
      while (!__all_sync(0xffffffffu, tag_ok(ya, tag) && tag_ok(yb, tag))) {
        if (!tag_ok(ya, tag)) ya = ld_relaxed4(ysrc);
        if (!tag_ok(yb, tag)) yb = ld_relaxed4(ysrc + NFFN * 4);
        watchdog(n);
      }
      __syncwarp();
      PROF(8, t3 == 0, 5);
      float y0 = untag_sum(ya.x, yb.x), y1 = untag_sum(ya.y, yb.y), y2 = untag_sum(ya.z, yb.z), y3 = untag_sum(ya.w, yb.w);
      const bool u1 = lane & 2, u2 = lane & 4;
      y0 = (u1 ? y2 : y0) + __shfl_xor_sync(0xffffffffu, u1 ? y0 : y2, 2);
      y1 = (u1 ? y3 : y1) + __shfl_xor_sync(0xffffffffu, u1 ? y1 : y3, 2);
      y0 = (u2 ? y1 : y0) + __shfl_xor_sync(0xffffffffu, u2 ? y0 : y1, 4);
      y0 += __shfl_xor_sync(0xffffffffu, y0, 8);
      if (!(lane & 8)) sts1(par + PAR_RED + 64 + (t3 >> 4) * 32 + ((lane & 1) * 4 + (lane & 2) + ((lane >> 2) & 1)) * 4, __float_as_uint(y0));
      bar_sync(4, 128);
      if (t3 < 4) {
        y0 = 0.f; y1 = 0.f;
#pragma unroll
        for (int w4 = 0; w4 < 7; w4++) {
          const uint2 v = lds2(par + PAR_RED + 64 + w4 * 32 + t3 * 8);
          y0 += __uint_as_float(v.x); y1 += __uint_as_float(v.y);
        }
        const uint2 gv = lds2(par + PAR_CONST + 16 + t3 * 8);
        const uint32_t upd = hmul2(pack_bf(y0, y1), pack_bf(rs, rs));
        *reinterpret_cast<uint32_t*>(P.out + (size_t)win.y * DM + b * 8 + t3 * 2) =
            hadd2(fx.x, hmul2(__byte_perm(gv.x, gv.y, 0x7632), hadd2(fh.x, upd)));
        if (b == 0 && t3 == 0) st_relaxed(&g_epoch, epoch + 1);
      }
      PROF(31, t3 == 0, 36);
    }
    cluster_wait();
  } else {
    const int wg = warp >> 2;

    uint32_t tag;
    {
      uint32_t* const pmod = g_modp + rank * 2 * DM + (b >> 1) * 32 + lane;
      uint32_t* const pln = g_ln1 + (rb * 128 + cj * 16 + warp) * 4;
      const uint32_t cv = ldg_nc1(P.c + rank * 512 + tid * 2);
      const uint32_t epoch = ld_relaxed(&g_epoch);
      if (warp == 0) st_relaxed(pmod, 0);
      if (lane == 0) { st_b128(pln, 0, 0, 0, 0); st_b128(pln + 32, 0, 0, 0, 0); }
      asm volatile("setmaxnreg.inc.sync.aligned.u32 232;");
      sts1(par + tid * 4, pack_bf(silu_f(bf_lo(cv)), silu_f(bf_hi(cv))));
      bar_sync(1, 320);
      tag = epoch % 3 + 1;
#pragma unroll
      for (int part = 0; part < 3; part++) {
        if (part != 1) {
          const uint32_t xa = base + (2 + part / 2) * GST_BYTES + warp * 2048 + lane * 16;
          mbar_wait(bar_hx + part * 4, 0);
          float s0 = 0.f, s1 = 0.f, q0 = 0.f, q1 = 0.f;
#pragma unroll
          for (int q = 0; q < 4; q++) {
            const uint4 xv = lds4(xa + q * 512);
            const uint32_t u[4] = {xv.x, xv.y, xv.z, xv.w};
#pragma unroll
            for (int e = 0; e < 4; e++) { const float lo = bf_lo(u[e]), hi = bf_hi(u[e]); s0 += lo; s1 += hi; q0 += lo * lo; q1 += hi * hi; }
          }
          s0 += s1; q0 += q1;
#pragma unroll
          for (int o = 16; o > 0; o >>= 1) { s0 += __shfl_xor_sync(0xffffffffu, s0, o); q0 += __shfl_xor_sync(0xffffffffu, q0, o); }
          const float mean = s0 * (1.f / DM);
          float mb, sd;
          ln_scalars(mean, fmaxf(q0 * (1.f / DM) - mean * mean, 0.f), mb, sd);
          uint32_t ih, il;
          split_inv(sd, ih, il);
          if (lane == 0) st_b128(pln + part * 16, pack_bf(mb, mb), ih, il, tag);
          PROF(1, tid == 0 && part == 2, 4);
        } else {
          const uint32_t fr = (lane & 7) + (lane >> 4) * 8, tq = lane & 3;
          const uint32_t wa = stage + warp * 4096 + fr * 64 + ((((lane >> 3) & 1) ^ ((fr >> 1) & 3)) << 4);
          uint32_t sc[8];
#pragma unroll
          for (int k = 0; k < 8; k++) sc[k] = lds1(par + warp * 128 + k * 16 + tq * 4);
          float d0[4] = {0.f, 0.f, 0.f, 0.f}, d1[4] = {0.f, 0.f, 0.f, 0.f};
          mbar_wait(bar_hw, 0);
#pragma unroll
          for (int ks = 0; ks < 4; ks++) {
            uint32_t w[8];
            ldmatrix4t(wa + ks * 1024, w[0], w[1], w[2], w[3]);
            ldmatrix4t((wa ^ 32) + ks * 1024, w[4], w[5], w[6], w[7]);
            mma16816(d0, w[0], w[1], w[2], w[3], sc[2 * ks], sc[2 * ks + 1]);
            mma16816(d1, w[4], w[5], w[6], w[7], sc[2 * ks], sc[2 * ks + 1]);
          }
          sts1(base + 2 * GST_BYTES + warp * 2048 + (tq * 8 + (lane >> 2)) * 4, __float_as_uint((tq & 2) ? ((tq & 1) ? d1[2] : d1[0]) : ((tq & 1) ? d0[2] : d0[0])));
          bar_sync(1, 256);
          if (warp == 0) {
            float s = 0.f;
#pragma unroll
            for (int w8 = 0; w8 < 8; w8++) s += __uint_as_float(lds1(base + 2 * GST_BYTES + w8 * 2048 + lane * 4));
            st_relaxed(pmod, (__float_as_uint(s) & ~3u) | tag);
          }
          PROF(1, tid == 0, 3);
        }
      }
      cluster_wait();
      if (wg == 1) bar_arrive(2, 256);
    }

    float f0 = 0.f, f1 = 0.f;
    const uint32_t rempty = lane < 2 ? mapa(bempty, lane & 1) : 0;
    constexpr uint32_t GE = NSLOT * 8 + 32;
    float o[64], s[64];
#pragma unroll 1
    for (int ps = 0; ps < 3; ps++) {
      {
        const uint32_t xt = ps == 1 ? XT1 : XT2, wt = ps == 1 ? WT1 : WT2;
        const int nst = ps == 2 ? 28 : 14;
        if (ps == 0) {
          float ga[64], gb[64];
#pragma unroll
          for (int i = 0; i < 64; i++) { ga[i] = 0.f; gb[i] = 0.f; }
          uint32_t a[2][16];
          const uint32_t l = fresh_lane();
          uint32_t fa[4];
#pragma unroll
          for (int kk = 0; kk < 4; kk++) fa[kk] = (base + wg * 8192 + frag_offset(warp)) ^ (kk * 32);
          const uint32_t mt = par + (l & 3) * 16;
          auto fetch = [&](int i, uint32_t (&f)[16], uint32_t z) {
            mbar_wait(xfull + (i & 3) * 8, i >> 2);
#pragma unroll
            for (int kk = 0; kk < 4; kk++) ldmatrix4(fa[kk] + (i & 3) * GST_BYTES + z, f[4 * kk], f[4 * kk + 1], f[4 * kk + 2], f[4 * kk + 3]);
          };
          uint4 r0, r1;
          {
            const uint32_t t7 = (warp & 3) * 32 + l;
            const uint32_t* pm = g_modp + wg * DM + ((cj * 128 + t7 * 4) & (DM - 1));
            const uint32_t* pr = g_ln1 + (rb * 128 + warp * 16 + (l >> 2)) * 4;
            uint4 m0 = ld_relaxed4(pm), m1 = ld_relaxed4(pm + 2 * DM);
            r0 = ld_b128(pr); r1 = ld_b128(pr + 32);
            fetch(0, a[0], 0); fetch(1, a[1], 0);
            uint32_t n = 0;
            bool written = false;
#pragma unroll 1
            while (true) {
              uint32_t miss;
              asm volatile("{ .reg .pred p0, p1, p2, p3; .reg .b32 t, u;\n"
                           "lop3.b32 t, %1, %2, %19, 0x7e; lop3.b32 u, %3, %4, %19, 0x7e; or.b32 t, t, u; and.b32 t, t, 3; setp.ne.u32 p0, t, 0;\n"
                           "lop3.b32 t, %5, %6, %19, 0x7e; lop3.b32 u, %7, %8, %19, 0x7e; or.b32 t, t, u; and.b32 t, t, 3; setp.ne.u32 p1, t, 0;\n"
                           "setp.ne.u32 p2, %12, %19; setp.ne.u32 p3, %16, %19;\n"
                           "@p0 ld.relaxed.gpu.global.v4.u32 {%1, %2, %3, %4}, [%17];\n"
                           "@p1 ld.relaxed.gpu.global.v4.u32 {%5, %6, %7, %8}, [%17 + 8192];\n"
                           "@p2 ld.relaxed.gpu.global.v4.u32 {%9, %10, %11, %12}, [%18];\n"
                           "@p3 ld.relaxed.gpu.global.v4.u32 {%13, %14, %15, %16}, [%18 + 128];\n"
                           "or.pred p0, p0, p1; or.pred p2, p2, p3; vote.sync.any.pred p0, p0, 0xffffffff; vote.sync.any.pred p2, p2, 0xffffffff;\n"
                           "selp.u32 t, 1, 0, p0; selp.u32 u, 2, 0, p2; or.b32 %0, t, u; }"
                           : "=r"(miss), "+r"(m0.x), "+r"(m0.y), "+r"(m0.z), "+r"(m0.w), "+r"(m1.x), "+r"(m1.y), "+r"(m1.z), "+r"(m1.w),
                             "+r"(r0.x), "+r"(r0.y), "+r"(r0.z), "+r"(r0.w), "+r"(r1.x), "+r"(r1.y), "+r"(r1.z), "+r"(r1.w)
                           : "l"(pm), "l"(pr), "r"(tag) : "memory");
              if (!(miss & 1) && !written) {
                written = true;
                float c0 = untag_sum(m0.x, m1.x), c1 = untag_sum(m0.y, m1.y), c2 = untag_sum(m0.z, m1.z), c3 = untag_sum(m0.w, m1.w);
                if (wg) { c0 = 1.f + rbf(c0); c1 = 1.f + rbf(c1); c2 = 1.f + rbf(c2); c3 = 1.f + rbf(c3); }
                const uint32_t d = par + (t7 >> 2) * 64 + (t7 & 1) * 32 + (t7 & 2) * 2 + (wg ? 0 : 8);
                sts1(d, pack_bf(c0, c1));
                sts1(d + 16, pack_bf(c2, c3));
                mbar_arrive(bar_mod);
              }
              if (!miss) break;
              watchdog(n);
            }
          }
          const uint32_t zero = r0.w ^ tag;
          auto normalize = [&](uint32_t (&f)[16]) {
#pragma unroll
            for (int k = 0; k < 16; k += 2) { f[k] = ln_norm(f[k], r0.x, r0.y, r0.z); f[k + 1] = ln_norm(f[k + 1], r1.x, r1.y, r1.z); }
          };
          auto modulate = [&](int i, uint32_t (&f)[16]) {
#pragma unroll
            for (int kk = 0; kk < 4; kk++) {
              const uint4 m = lds4(mt + i * 256 + kk * 64);
              f[4 * kk] = MODUL(f[4 * kk], m.x, m.z); f[4 * kk + 1] = MODUL(f[4 * kk + 1], m.x, m.z);
              f[4 * kk + 2] = MODUL(f[4 * kk + 2], m.y, m.w); f[4 * kk + 3] = MODUL(f[4 * kk + 3], m.y, m.w);
            }
            keep(f);
            mbar_arrive_pred(xempty + (i & 3) * 8, l == 0);
          };
          auto publish = [&](int u, uint32_t (&f)[16]) {
#pragma unroll
            for (int kk = 0; kk < 4; kk++) stmatrix4(fa[kk] + OFF_STAGE + u * UNIT, f[4 * kk], f[4 * kk + 1], f[4 * kk + 2], f[4 * kk + 3]);
            __syncwarp();
            mbar_arrive_pred(bar_hpub + u * 8, l == 0);
          };
          auto multiply = [&](int i, uint32_t (&f)[16]) {
            mbar_wait(gfull + (i & 3) * 8, i >> 2);
            const uint64_t db = make_desc(base + (i & 3) * GST_BYTES + UNIT, 8192, 1024);
            wg_fence();
#pragma unroll
            for (int kk = 0; kk < 4; kk++) mma256_rs(ga, gb, f[4 * kk], f[4 * kk + 1], f[4 * kk + 2], f[4 * kk + 3], db + kk * 128);
            wg_commit();
          };
          auto next = [&](int i, uint32_t (&f)[16]) {
            wg_wait<1>();
            mbar_arrive_cl(rempty, GE + ((i + 2) & 3) * 8);
            uint32_t z = zero;
#pragma unroll
            for (int k = 0; k < 16; k += 2) asm volatile("lop3.b32 %0, %1, %2, %0, 0xA8;" : "+r"(z) : "r"(f[k]), "r"(f[k + 1]));
            fetch(i, f, z);
            normalize(f); modulate(i, f); multiply(i, f);
          };
          normalize(a[0]); normalize(a[1]);
          keep(a[0]); keep(a[1]);
          mbar_wait(bar_mod, 0);
          PROF(1, tid == 0, 2);
          modulate(0, a[0]); multiply(0, a[0]); publish(0, a[0]);
          modulate(1, a[1]); multiply(1, a[1]); publish(1, a[1]);
#pragma unroll 1
          for (int i = 2; i < NRS; i += 2) { next(i, a[0]); next(i + 1, a[1]); }
          wg_wait<1>();
          mbar_arrive_cl(rempty, GE + ((NRS + 2) & 3) * 8);
#pragma unroll 1
          for (int i = NRS; i < 14; i++) {
            mbar_wait(xfull + (i & 3) * 8, (i >> 2) & 1);
            mbar_wait(gfull + (i & 3) * 8, (i >> 2) & 1);
            const uint32_t xa = base + (i & 3) * GST_BYTES;
            const uint64_t da = make_desc(xa + wg * 8192, 16, 1024), db = make_desc(xa + UNIT, 8192, 1024);
            if (i == 13) bar_sync(2 + wg, 256);
            wg_fence();
#pragma unroll
            for (int kk = 0; kk < 4; kk++) mma256_ss(ga, gb, da + kk * 2, db + kk * 128, 1);
            wg_commit();
            if (i == 13) bar_arrive(3 - wg, 256);
            wg_wait<1>();
            uint32_t z = zero;
#pragma unroll
            for (int k = 0; k < 16; k += 2) asm volatile("lop3.b32 %0, %1, %2, %0, 0xA8;" : "+r"(z) : "r"(a[1][k]), "r"(a[1][k + 1]));
            mbar_arrive_cl(rempty, GE + ((i + 3) & 3) * 8 + z);
            mbar_arrive_pred(xempty + ((i + 3) & 3) * 8, l == 0 && i != NRS);
          }
          mbar_wait(xfull + 16, 1);
          wg_wait<0>();
          keep(ga); keep(gb);
#pragma unroll
          for (int i = 0; i < 64; i++) {
            asm volatile("mov.b32 %0, %1;" : "=f"(s[i]) : "f"(ga[i]));
            asm volatile("mov.b32 %0, %1;" : "=f"(o[i]) : "f"(gb[i]));
          }
        } else {
          float ga[64], gb[64];
#pragma unroll
          for (int i = 0; i < 64; i++) {
            asm volatile("mov.b32 %0, %1;" : "=f"(ga[i]) : "f"(s[i]));
            asm volatile("mov.b32 %0, %1;" : "=f"(gb[i]) : "f"(o[i]));
          }
#pragma unroll 1
          for (int i = 0; i < nst; i++) {
            mbar_wait(gfull + (i & 3) * 8, (i >> 2) & 1);
            const uint64_t da = make_desc(base + unit_of(xt, i & 3) + wg * 8192, 16, 1024), db = make_desc(base + unit_of(wt, i & 3), 8192, 1024);
            if (i == nst - 1) bar_sync(2 + wg, 256);
            wg_fence();
#pragma unroll
            for (int kk = 0; kk < 4; kk++) mma256_ss(ga, gb, da + kk * 2, db + kk * 128, kk ? 1 : i);
            wg_commit();
            if (i == nst - 1) bar_arrive(3 - wg, 256);
            wg_wait<1>();
            mbar_arrive_cl(rempty, GE + ((i + 3) & 3) * 8, i != 0);
            PROF(4, tid == 0 && (i & 3) == 0, 40 + (ps - 1) * 4 + i / 4);
          }
          wg_wait<0>();
          keep(ga); keep(gb);
#pragma unroll
          for (int i = 0; i < 64; i++) {
            asm volatile("mov.b32 %0, %1;" : "=f"(s[i]) : "f"(ga[i]));
            asm volatile("mov.b32 %0, %1;" : "=f"(o[i]) : "f"(gb[i]));
          }
        }
        mbar_arrive_cl(rempty, GE + (ps == 2 ? 24 : 8));
        if (ps == 2) break;
      }
      const uint32_t qw = base + wg * 8192, qt = QT >> (16 * ps), at = ps ? AT1 : AT0;
      {
        const uint32_t wt = ps ? WT1 : WT0;
        const uint64_t da0 = make_desc(qw + unit_of(qt, 2), 16, 1024), da1 = make_desc(qw + unit_of(qt, 3), 16, 1024);
        const uint64_t db0 = make_desc(base + unit_of(wt, 2), 8192, 1024), db1 = make_desc(base + unit_of(wt, 3), 8192, 1024);
        mbar_wait(gfull + 16, 1);
        bar_sync(2 + wg, 256);
        wg_fence();
#pragma unroll
        for (int kk = 0; kk < 4; kk++) mma_ss<1>(s, da0 + kk * 2, db0 + kk * 128, 1);
        wg_commit();
        mbar_wait(xfull + 24, 1);
        mbar_wait(gfull + 24, 1);
        wg_fence();
#pragma unroll
        for (int kk = 0; kk < 4; kk++) mma_ss<1>(s, da1 + kk * 2, db1 + kk * 128, 1);
        wg_commit();
        bar_arrive(3 - wg, 256);
        mbar_wait(ps == 0 ? bar_pread : bar_ofree + 8, 0);
        wg_wait<0>();
        keep(s);
        PROF(2, tid == 0, 8 + ps * 8);
        uint32_t q[32];
        pack_p(s, q);
#pragma unroll
        for (int i = 0; i < 4; i++) stmatrix4((qw + unit_of(qt, 0) + frag_offset(warp)) ^ (i << 5), q[4 * i], q[4 * i + 1], q[4 * i + 2], q[4 * i + 3]);
        keep(q);
        bar_sync(2 + wg, 256);
        wg_fence();
#pragma unroll
        for (int kk = 0; kk < 8; kk++) mma_ss<1>(o, (kk < 4 ? da0 : da1) + (kk & 3) * 2, (kk < 4 ? db0 : db1) + UNIT / 16 + (kk & 3) * 128, 1);
        wg_commit();
        mbar_wait(bfull, 0);
        wg_fence();
        const uint64_t dk = make_desc(base + unit_of(at, 0), 16, 1024);
#pragma unroll
        for (int kk = 0; kk < 8; kk++) mma_rs<0>(s, q[4 * kk], q[4 * kk + 1], q[4 * kk + 2], q[4 * kk + 3], dk + (kk >> 2) * 1024 + (kk & 3) * 2, kk != 0);
        wg_commit();
        bar_arrive(3 - wg, 256);
#pragma unroll
        for (int i = 4; i < 8; i++) stmatrix4((qw + unit_of(qt, 1) + frag_offset(warp)) ^ ((i & 3) << 5), q[4 * i], q[4 * i + 1], q[4 * i + 2], q[4 * i + 3]);
        wg_wait<1>();
        keep(o);
        mbar_arrive_cl(rempty, GE + 16);
        mbar_arrive_cl(rempty, GE + 24);
        store_chunk<0>(o, qw + unit_of(qt, 2) + frag_offset(warp));
        store_chunk<1>(o, qw + unit_of(qt, 3) + frag_offset(warp));
        wg_wait<0>();
        keep(s);
        mbar_arrive_cl(rempty, 0);
      }
      PROF(4, tid == 0 && ps == 1, 61);
      float l0 = 0.f, l1 = 0.f;
      auto step = [&](auto odd_c, const int j, uint32_t (&pw)[32], uint32_t (&pr)[32]) {
        constexpr bool ODD = decltype(odd_c)::value;
        const bool first = !ODD && (j & 2) == 0, last = ODD && j == 7;
        const uint32_t ph = (j >> 1) & 1;
        float i0, i1, a0, a1;
        const bool so = !ODD && j == 4;
        if (so) { i0 = inv_quad_sum(l0); i1 = inv_quad_sum(l1); l0 = 0.f; l1 = 0.f; }
        bool redo = !ODD && (j | ps) == 0;
        while (true) {
          if (redo) {
            float m0 = fmaxf(s[0], s[1]), m1 = fmaxf(s[2], s[3]);
#pragma unroll
            for (int i = 1; i < 16; i++) { m0 = fmaxf(m0, fmaxf(s[4 * i], s[4 * i + 1])); m1 = fmaxf(m1, fmaxf(s[4 * i + 2], s[4 * i + 3])); }
            m0 = fmaxf(m0, __shfl_xor_sync(0xffffffffu, m0, 1)); m1 = fmaxf(m1, __shfl_xor_sync(0xffffffffu, m1, 1));
            m0 = fmaxf(m0, __shfl_xor_sync(0xffffffffu, m0, 2)); m1 = fmaxf(m1, __shfl_xor_sync(0xffffffffu, m1, 2));
            m0 *= SCL2; m1 *= SCL2;
            if (!first) {
              m0 = fmaxf(m0, f0); m1 = fmaxf(m1, f1);
              const float c0 = ex2(f0 - m0), c1 = ex2(f1 - m1);
              l0 *= c0; l1 *= c1;
              wg_wait<0>();
              keep(o);
#pragma unroll
              for (int i = 0; i < 16; i++) { o[4 * i] *= c0; o[4 * i + 1] *= c0; o[4 * i + 2] *= c1; o[4 * i + 3] *= c1; }
            }
            f0 = m0; f1 = m1;
          }
          float b0 = 0.f, b1 = 0.f;
          a0 = 0.f; a1 = 0.f;
#pragma unroll
          for (int i = 0; i < 16; i++) {
            const float e0 = ex2(fmaf(s[4 * i], SCL2, -f0)), e1 = ex2(fmaf(s[4 * i + 1], SCL2, -f0));
            const float e2 = ex2(fmaf(s[4 * i + 2], SCL2, -f1)), e3 = ex2(fmaf(s[4 * i + 3], SCL2, -f1));
            a0 += e0; b0 += e1; a1 += e2; b1 += e3;
            pw[2 * i] = pack_bf(e0, e1); pw[2 * i + 1] = pack_bf(e2, e3);
            if (i == VREL) {
#pragma unroll
              for (int k = 0; k < 2 * VREL + 2; k++) asm volatile("" : "+r"(pw[k])::"memory");
              mbar_wait(bar_mod, 0);
              wg_wait<0>();
              mbar_arrive_cl(rempty, ODD ? 16 : 0, !redo && (ODD || j));
#pragma unroll
              for (int k = 4 * VREL + 4; k < 64; k++) asm volatile("" : "+f"(s[k])::"memory");
            }
          }
          a0 += b0; a1 += b1;
          if (redo) break;
          redo = __any_sync(0xffffffffu, !(a0 + a1 < 0x1p90f));
          if (first) {
            uint32_t m0 = __ballot_sync(0xffffffffu, a0 > 0x1p-80f), m1 = __ballot_sync(0xffffffffu, a1 > 0x1p-80f);
            m0 |= m0 >> 1; m1 |= m1 >> 1; m0 |= m0 >> 2; m1 |= m1 >> 2;
            redo = redo || (m0 & m1 & 0x11111111u) != 0x11111111u;
          }
          if (!redo) break;
        }
        l0 += a0; l1 += a1;
        keep(pw);
        keep(o);
        if (so) store_chunk<0>(o, i0, i1, qw + unit_of(qt, 0) + frag_offset(warp));
        keep(o);
        if (j == (ODD ? 5 : 0)) { fence_async_smem(); if (ODD) mbar_arrive(bar_ofull + wg * 8); }
        mbar_wait(bfull + (ODD ? 24 : 8), ph);
        bar_sync(2 + wg, 256);
        if (!last) {
          const uint32_t qn = qt >> (j >= 3 ? 8 : 0);
          wg_fence();
          issue_qk(s, qw + unit_of(qn, 0), qw + unit_of(qn, 1), base + unit_of(at, ODD ? 3 : 1));
          wg_commit();
          mbar_wait(bfull + (ODD ? 0 : 16), ODD ? ph ^ 1 : ph);
        }
        if (so) { store_chunk<1>(o, i0, i1, qw + unit_of(qt, 1) + frag_offset(warp)); keep(o); }
        wg_fence();
        issue_pv(o, pw, base + unit_of(at, ODD ? (last ? 3 : 0) : 2), !first);
        wg_commit();
        bar_arrive(3 - wg, 256);
        wg_wait<1>();
        keep(s);
        mbar_arrive_cl(rempty, ODD ? 24 : 8, !last);
        PROF(4, tid == 0 && ps == 1, 51 + j);
      };
      uint32_t pa[32], pb[32];
#pragma unroll 1
      for (int j = 0; j < 8; j += 2) {
        step(std::false_type{}, j, pa, pb);
        step(std::true_type{}, j + 1, pb, pa);
      }
      {
        const float i0 = inv_quad_sum(l0), i1 = inv_quad_sum(l1);
        wg_wait<0>();
        keep(o);
        mbar_arrive_cl(rempty, 24);
        store_chunk<0>(o, i0, i1, qw + unit_of(qt, 2) + frag_offset(warp));
        store_chunk<1>(o, i0, i1, qw + unit_of(qt, 3) + frag_offset(warp));
        fence_async_smem();
        mbar_arrive(bar_ofull + 16 + wg * 8);
      }
      PROF(2, tid == 0, 10 + ps * 8);
    }

    const int ln = fresh_lane(), g = ln >> 2, tq = ln & 3, ct = warp * 32 + ln;
    const bool lane0 = ln == 0;
    const int lrow0 = warp * 16 + g;
    const int grow0 = rb * 128 + lrow0;
    const uint32_t res = base + OFF_RES, trow = res + wg * 8192 + frag_offset(warp);
    uint32_t xr[32];
    uint4 sv[4], own;
    uint32_t* sp[4];
#pragma unroll
    for (int k = 0; k < 4; k++) sp[k] = g_stats + ((((tq >> 1) * 4 + k) ^ cj) * SEQ + grow0 + (tq & 1) * 8) * 4;
    {
      const uint64_t da = make_desc(base + wg * 8192, 16, 1024), db = make_desc(base, 8192, 1024);
      constexpr int U = UNIT / 16;
#define HALF_STAGE(acc, xu, wu) _Pragma("unroll") for (int kk = 0; kk < 4; kk++) mma_ss<1>(acc, da + (xu) * U + kk * 2, db + (wu) * U + kk * 128, 1)
      PROF(10, ct == PT, 19); STAMP(0);
      cluster_arrive();
      mbar_wait(gfull, 1);
      mbar_wait(gfull + 8, 1);
      bar_sync(2 + wg, 256);
      wg_fence();
      HALF_STAGE(o, 7, 1);
      HALF_STAGE(o, 8, 3);
      wg_commit();
      STAMP(16);
      mbar_wait(gfull + 16, 1);
      STAMP(17);
      wg_fence();
      HALF_STAGE(o, 6, 11);
      wg_commit();
      bar_arrive(3 - wg, 256);
      mbar_wait(bar_par, 0);
      uint32_t* xo = g_xch + ((size_t)b * 8 * 256 + ct) * 4;
      const uint32_t* xi = g_xch + ((size_t)(b ^ 2) * 8 * 256 + ct) * 4;
      const uint32_t par1 = (~lds1(par + PAR_CONST + 4) & 1) << 16;
      wg_wait<1>();
      mbar_arrive_pred(bar_rel, lane0);
      wg_wait<0>();
      keep(o);
      mbar_arrive_pred(bar_ring, lane0);
      PROF(8, ct == PT, 20); STAMP(1);
#define SEND(i) st_b128(xo + (i) * 1024, (pack_bf(o[8 * (i)], o[8 * (i) + 1]) & ~0x10000u) | par1, pack_bf(o[8 * (i) + 2], o[8 * (i) + 3]), \
                        pack_bf(o[8 * (i) + 4], o[8 * (i) + 5]), pack_bf(o[8 * (i) + 6], o[8 * (i) + 7]))
#pragma unroll
      for (int i = 0; i < NS1; i++) SEND(i);
      PROF(8, ct == PT, 21); STAMP(2);
      bar_sync(2 + wg, 256);
      wg_fence();
      HALF_STAGE(s, 7, 0);
      HALF_STAGE(s, 8, 2);
      HALF_STAGE(s, 6, 10);
      wg_commit();
      bar_arrive(3 - wg, 256);
      STAMP(18);
      mbar_wait(gfull + 24, 1);
#pragma unroll
      for (int i = NS1; i < 8; i++) SEND(i);
      uint4 v[8];
#pragma unroll
      for (int i = 0; i < LD1; i++) v[i] = ld_b128(xi + i * 1024);
      STAMP(19);
      mbar_wait(bar_xres, 0);
      wg_wait<0>();
      mbar_arrive_pred(bar_ring + 8, lane0);
      bar_sync(2 + wg, 256);
      STAMP(20);
#pragma unroll
      for (int i = LD1; i < LD2; i++) v[i] = ld_b128(xi + i * 1024);
      mbar_wait(bar_xres, 0);
      wg_fence();
      HALF_STAGE(s, 9, 4);
      wg_commit();
      mbar_wait(bar_rx, 0);
      wg_fence();
      HALF_STAGE(s, 1, 5);
      wg_commit();
      bar_arrive(3 - wg, 256);
      STAMP(21);
#pragma unroll
      for (int i = LD2; i < 8; i++) v[i] = ld_b128(xi + i * 1024);
      if (LD2 < 8) mbar_wait(bar_xres, 0);
      wg_wait<0>();
      keep(s);
      mbar_arrive_pred(bar_ring + 16, lane0);
      PROF(10, ct == PT, 23); STAMP(4);
#pragma unroll
      for (int i = 0; i < 16; i += 2) ldmatrix4((trow ^ ((i & 7) << 4)) + (i >> 3) * 16384, xr[2 * i], xr[2 * i + 1], xr[2 * i + 2], xr[2 * i + 3]);
      uint32_t ga[16];
      uint4 bw[8];
#pragma unroll
      for (int i = 0; i < 8; i++) {
        if (!(i & 1)) {
          const uint4 t = lds4(par + PAR_SINK + i * 32 + tq * 16);
          ga[2 * i] = t.x; ga[2 * i + 1] = t.y; ga[2 * i + 2] = t.z; ga[2 * i + 3] = t.w;
        }
        bw[i] = lds4(par + PAR_T1 + i * 64 + tq * 16);
        if (!(g & 1)) { bw[i].x = 0x3f803f80u; bw[i].y = 0x3f803f80u; }
      }
      uint32_t pk[32];
      pack_p(s, pk);
      keep(pk);
      {
        uint32_t n = 0, miss;
        do {
          miss = 0;
#pragma unroll
          for (int i = 0; i < 8; i++) miss |= v[i].x ^ par1;
          miss = __any_sync(0xffffffffu, miss & 0x10000u);
          if (miss) {
#pragma unroll
            for (int i = 0; i < 8; i++)
              asm volatile("{ .reg .pred p; .reg .b32 t; xor.b32 t, %0, %5; and.b32 t, t, 0x10000; setp.ne.u32 p, t, 0;\n"
                           "@p ld.relaxed.gpu.global.v4.u32 {%0, %1, %2, %3}, [%4]; }"
                           : "+r"(v[i].x), "+r"(v[i].y), "+r"(v[i].z), "+r"(v[i].w) : "l"(xi + i * 1024), "r"(par1) : "memory");
          }
          watchdog(n);
        } while (miss);
      }
      PROF(8, ct == PT, 22); STAMP(3);
      float ds[4] = {0.f, 0.f, 0.f, 0.f}, dl[4] = {0.f, 0.f, 0.f, 0.f}, q0[4] = {0.f, 0.f, 0.f, 0.f}, q1[4] = {0.f, 0.f, 0.f, 0.f};
#pragma unroll
      for (int i = 0; i < 8; i++) {
        const uint32_t u0 = hfma2(ga[2 * i], hadd2(pk[4 * i], v[i].x & ~0x10000u), xr[4 * i]);
        const uint32_t u1 = hfma2(ga[2 * i], hadd2(pk[4 * i + 1], v[i].y), xr[4 * i + 1]);
        const uint32_t u2 = hfma2(ga[2 * i + 1], hadd2(pk[4 * i + 2], v[i].z), xr[4 * i + 2]);
        const uint32_t u3 = hfma2(ga[2 * i + 1], hadd2(pk[4 * i + 3], v[i].w), xr[4 * i + 3]);
        xr[4 * i] = u0; xr[4 * i + 1] = u1; xr[4 * i + 2] = u2; xr[4 * i + 3] = u3;
        mma16816(ds, u0, u1, u2, u3, bw[i].x, bw[i].y);
        mma16816(dl, u0, u1, u2, u3, bw[i].z, bw[i].w);
        mma16816(q0, u0, u1, u2, u3, u0, u2);
        mma16816(q1, u0, u1, u2, u3, u1, u3);
      }
      const float sqa = __shfl_sync(0xffffffffu, (g & 1) ? q0[1] : q0[0], g * 4 + (g >> 1));
      const float sqb = __shfl_sync(0xffffffffu, (g & 1) ? q1[3] : q1[2], g * 4 + (g >> 1));
      own = (tq & 1) ? make_uint4(__float_as_uint(ds[2]), __float_as_uint(sqb), __float_as_uint(ds[3] + dl[3]), tag)
                                 : make_uint4(__float_as_uint(ds[0]), __float_as_uint(sqa), __float_as_uint(ds[1] + dl[1]), tag);
      if (tq < 2) st_b128(sp[0], own.x, own.y, own.z, own.w);
#pragma unroll
      for (int k = 0; k < 4; k++) sv[k] = make_uint4(0, 0, 0, 0);
    }
    PROF(8, ct == PT, 29); STAMP(5);
    uint32_t mm, ih, il;
    float rbest;
    uint32_t wf[128];
    const uint32_t frow = (ln & 7) + (ln >> 4) * 8;
    const uint32_t wfo = base + (warp & 1) * 8192 + frow * 64 + ((((ln >> 3) & 1) ^ ((frow >> 1) & 3)) << 4);
#define LOAD_WF(m) _Pragma("unroll") for (int f = 0; f < 16; f++) {                                                   \
      const int r = ((f >> 1) * 4 + (m) * 2 + (f & 1)) * 4;                                                           \
      ldmatrix4t(((wfo + unit_of((m) ? FT_U : FT_G, warp >> 1)) ^ ((f & 1) * 32)) + (f >> 1) * 1024, wf[r], wf[r + 1], wf[r + 2], wf[r + 3]); \
    }
    bool early;
    {
#pragma unroll
      for (int i = 0; i < 16; i += 2) stmatrix4((trow ^ ((i & 7) << 4)) + (i >> 3) * 16384, xr[2 * i], xr[2 * i + 1], xr[2 * i + 2], xr[2 * i + 3]);
      const uint4 cst = lds4(par + PAR_CONST);
      const float A1 = __uint_as_float(cst.x), A2 = __uint_as_float(cst.z);
      uint32_t n = 0;
      early = false;
#pragma unroll 1
      while (true) {
        uint32_t miss;
        asm volatile("{ .reg .pred p0, p1, p2, p3; .reg .b64 u, v; .reg .b128 w;\n"
                     "setp.ge.u32 p0, %22, 2; setp.ne.and.u32 p0, %4, %21, p0; setp.ne.u32 p1, %8, %21; setp.ne.u32 p2, %12, %21; setp.ne.u32 p3, %16, %21;\n"
                     "@p0 ld.relaxed.gpu.global.v4.u32 {%1, %2, %3, %4}, [%17];\n"
                     "@p1 ld.relaxed.gpu.global.v4.u32 {%5, %6, %7, %8}, [%18];\n"
                     "@p2 ld.relaxed.gpu.global.v4.u32 {%9, %10, %11, %12}, [%19];\n"
                     "@p3 ld.relaxed.gpu.global.v4.u32 {%13, %14, %15, %16}, [%20];\n"
                     "or.pred p0, p0, p1; or.pred p2, p2, p3; or.pred p0, p0, p2; vote.sync.any.pred p0, p0, 0xffffffff; selp.u32 %0, 1, 0, p0; }"
                     : "=r"(miss), "+r"(sv[0].x), "+r"(sv[0].y), "+r"(sv[0].z), "+r"(sv[0].w), "+r"(sv[1].x), "+r"(sv[1].y), "+r"(sv[1].z), "+r"(sv[1].w),
                       "+r"(sv[2].x), "+r"(sv[2].y), "+r"(sv[2].z), "+r"(sv[2].w), "+r"(sv[3].x), "+r"(sv[3].y), "+r"(sv[3].z), "+r"(sv[3].w)
                     : "l"(sp[0]), "l"(sp[1]), "l"(sp[2]), "l"(sp[3]), "r"(tag), "r"(tq) : "memory");
        if (!miss) break;
        if (!early && (b >= NFFN || __all_sync(0xffffffffu, mbar_test(bar_box + (warp >> 1) * 8, 0)))) {
          early = true;
          LOAD_WF(0);
          __syncwarp();
          mbar_arrive_pred(bar_gate, lane0);
        }
        watchdog(n);
      }
      const uint4 v0 = tq < 2 ? own : sv[0], v1 = sv[1], v2 = sv[2], v3 = sv[3];
      PROF(8, ct == PT, 30); STAMP(6);
      float su = (__uint_as_float(v0.x) + __uint_as_float(v1.x)) + (__uint_as_float(v2.x) + __uint_as_float(v3.x));
      float sq = (__uint_as_float(v0.y) + __uint_as_float(v1.y)) + (__uint_as_float(v2.y) + __uint_as_float(v3.y));
      float dt = (__uint_as_float(v0.z) + __uint_as_float(v1.z)) + (__uint_as_float(v2.z) + __uint_as_float(v3.z));
      su += __shfl_xor_sync(0xffffffffu, su, 2); sq += __shfl_xor_sync(0xffffffffu, sq, 2); dt += __shfl_xor_sync(0xffffffffu, dt, 2);
      const float m = su * (1.f / DM);
      float mb, sd;
      ln_scalars(m, fmaxf(sq * (1.f / DM) - m * m, 0.f), mb, sd);
      const float inv = rcp(sd);
      rbest = (dt - mb * A1) * inv + A2;
      mm = pack_bf(mb, mb);
      ih = pack_bf(inv, inv);
      const float lo = inv - bf_lo(ih);
      il = pack_bf(lo, lo);
    }
    int ibest;
    {
      const uint32_t bits = __float_as_uint(rbest);
      const uint32_t key = (((int)bits < 0 ? ~bits : bits | 0x80000000u) & ~0x1ffu) | ((127 - lrow0 - (tq & 1) * 8) << 2) | tag;
      sts1(par + PAR_RED + warp * 4, __reduce_max_sync(0xffffffffu, key));
      PROF(8, ct == PT, 38); STAMP(7);
      bar_sync(1, 256);
      const uint4 ka = lds4(par + PAR_RED), kb = lds4(par + PAR_RED + 16);
      const uint32_t k2 = max(max(max(ka.x, ka.y), max(ka.z, ka.w)), max(max(kb.x, kb.y), max(kb.z, kb.w)));
      if (ct == 0 && cj == 0) st_relaxed(g_cand + rb, k2);
      ibest = 127 - ((k2 >> 2) & 127);
    }
    PROF(8, ct == PT, 39); STAMP(8);
    if ((ibest >> 4) == warp) {
      const int src = (ibest & 7) * 4 + ((ibest >> 3) & 1), ch = g * 2;
      const uint32_t cm = __shfl_sync(0xffffffffu, mm, src), ch_ = __shfl_sync(0xffffffffu, ih, src), cl = __shfl_sync(0xffffffffu, il, src);
      const uint32_t xa = res + (ch >> 3) * 16384 + ibest * 128 + (((ch & 7) ^ (ibest & 7)) << 4) + tq * 4;
      const uint32_t x0 = lds1(xa), x1 = lds1(xa ^ 16);
      const uint2 p0 = lds2(par + PAR_T2 + ch * 64 + tq * 16), p1 = lds2(par + PAR_T2 + ch * 64 + 64 + tq * 16);
      uint32_t* dst = g_row + rb * 2 * DM + cj * 128 + ln * 4;
      st_pairs(dst, ln_mod(x0, cm, ch_, cl, p0.x, p0.y), ln_mod(x1, cm, ch_, cl, p1.x, p1.y), tag);
      st_pairs(dst + DM, x0, x1, tag);
      __syncwarp();
    }
    PROF(8, ct == PT, 37); STAMP(9);
    uint32_t wd[64];
    const uint32_t wda = base + unit_of(FT_D, warp >> 1) + (warp & 1) * 8192 + frow * 128 + ((((ln >> 3) & 1) ^ (ln & 7)) << 4);
#define LOAD_WD(f) ldmatrix4t((wda ^ ((((f) >> 1) & 3) * 32)) + ((f) >> 3) * 4096 + ((f) & 1) * 2048, wd[4 * (f)], wd[4 * (f) + 1], wd[4 * (f) + 2], wd[4 * (f) + 3])
    if (!early) {
      if (b < NFFN) mbar_wait(bar_box + (warp >> 1) * 8, 0);
      LOAD_WF(0);
      __syncwarp();
      mbar_arrive_pred(bar_gate, lane0);
    }
    if (b < NFFN) {
      const uint32_t own = base + unit_of(FT_G, warp >> 1) + (warp & 1) * 8192;
      mbar_wait(bar_box + (4 + (warp >> 1)) * 8, 0);
      LOAD_WF(1);
      uint32_t* const ydst = g_ypart + ((size_t)(warp * 16 + tq * 2) * NFFN + b) * 8 + g;
      PROF(8, ct == PT, 31); STAMP(10);
      bool wdok;
      {
        uint32_t n = 0;
        while (!(wdok = __all_sync(0xffffffffu, mbar_test(bar_box + (8 + (warp >> 1)) * 8, 0))) && !__all_sync(0xffffffffu, mbar_test(bar_sel, 0))) watchdog(n);
      }
      if (wdok) {
#pragma unroll
        for (int f = 0; f < 16; f++) LOAD_WD(f);
      }
      STAMP(11);
      mbar_wait(bar_sel, 0);
      PROF(8, ct == PT, 33); STAMP(12);
      float d[8][4];
#pragma unroll
      for (int i = 0; i < 4; i++) { d[i][0] = 0.f; d[i][1] = 0.f; d[i][2] = 0.f; d[i][3] = 0.f; }
#pragma unroll
      for (int ks = 0; ks < 8; ks++) {
        const uint2 hb = lds2(own + 256 + ks * 32 + tq * 8);
#pragma unroll
        for (int mt = 0; mt < 4; mt++) {
          const int r = ks * 16 + mt * 4;
          mma16816(d[mt], wf[r], wf[r + 1], wf[r + 2], wf[r + 3], hb.x, hb.y);
        }
      }
      sts2(own + (tq * 8 + g) * 8, __float_as_uint((tq & 2) ? ((tq & 1) ? d[1][2] : d[1][0]) : ((tq & 1) ? d[0][2] : d[0][0])),
           __float_as_uint((tq & 2) ? ((tq & 1) ? d[3][2] : d[3][0]) : ((tq & 1) ? d[2][2] : d[2][0])));
      bar_sync(1, 256);
      uint32_t ab[4];
      {
        float G = 0.f, U = 0.f;
        uint2 pv[8];
#pragma unroll
        for (int w8 = 0; w8 < 8; w8++) pv[w8] = lds2(base + ln * 8 + ((FT_G >> (w8 >> 1) * 4) & 15) * UNIT + (w8 & 1) * 8192);
#pragma unroll
        for (int w8 = 0; w8 < 8; w8 += 2) {
          G += __uint_as_float(pv[w8].x) + __uint_as_float(pv[w8 + 1].x);
          U += __uint_as_float(pv[w8].y) + __uint_as_float(pv[w8 + 1].y);
        }
        const float act = rbf(silu_f(rbf(G))) * rbf(U);
        const uint32_t pk = pack_bf(act, __shfl_down_sync(0xffffffffu, act, 1));
#pragma unroll
        for (int i = 0; i < 4; i++) ab[i] = __shfl_sync(0xffffffffu, pk, i * 8 + tq * 2);
      }
      if (!wdok) {
        mbar_wait(bar_box + (8 + (warp >> 1)) * 8, 0);
#pragma unroll
        for (int f = 0; f < 16; f++) LOAD_WD(f);
      }
      PROF(8, ct == PT, 34); STAMP(13);
#pragma unroll
      for (int mt = 0; mt < 8; mt++) {
        d[mt][0] = 0.f; d[mt][1] = 0.f; d[mt][2] = 0.f; d[mt][3] = 0.f;
        mma16816(d[mt], wd[mt * 8], wd[mt * 8 + 1], wd[mt * 8 + 2], wd[mt * 8 + 3], ab[0], ab[1]);
        mma16816(d[mt], wd[mt * 8 + 4], wd[mt * 8 + 5], wd[mt * 8 + 6], wd[mt * 8 + 7], ab[2], ab[3]);
      }
#pragma unroll
      for (int i = 0; i < 4; i++) {
        const int m4 = (i >> 1) * 4, e = (i & 1) * 2;
        const float y = (tq & 2) ? ((tq & 1) ? d[m4 + 3][e] : d[m4 + 2][e]) : ((tq & 1) ? d[m4 + 1][e] : d[m4][e]);
        st_relaxed(ydst + (m4 * 2 + (i & 1)) * NFFN * 8, tagf(y, tag));
      }
      PROF(8, ct == PT, 35); STAMP(14);
    }
    mbar_wait(bar_sel, 0);
    mbar_arrive_pred(bar_win, ct == 0);
    const int iwin = lds1(par + PAR_CONST + 60) & 0x7ff;
    const bool cand = (iwin >> 4) == rb * 8 + warp;
    {
      const uint32_t mm0 = __shfl_sync(0xffffffffu, mm, ln & ~1), mm1 = __shfl_sync(0xffffffffu, mm, ln | 1);
      const uint32_t ih0 = __shfl_sync(0xffffffffu, ih, ln & ~1), ih1 = __shfl_sync(0xffffffffu, ih, ln | 1);
      const uint32_t il0 = __shfl_sync(0xffffffffu, il, ln & ~1), il1 = __shfl_sync(0xffffffffu, il, ln | 1);
#pragma unroll 1
      for (int hf = 0; hf < 2; hf++) {
        uint32_t x[16];
#pragma unroll
        for (int i = 0; i < 8; i += 2) ldmatrix4((trow ^ (i << 4)) + hf * 16384, x[2 * i], x[2 * i + 1], x[2 * i + 2], x[2 * i + 3]);
#pragma unroll
        for (int i = 0; i < 8; i++) {
          const uint4 pv = lds4(par + PAR_T2 + (hf * 8 + i) * 64 + tq * 16);
          x[2 * i] = hadd2(x[2 * i], hmul2(pv.z, ln_mod(x[2 * i], mm0, ih0, il0, pv.x, pv.y)));
          x[2 * i + 1] = hadd2(x[2 * i + 1], hmul2(pv.z, ln_mod(x[2 * i + 1], mm1, ih1, il1, pv.x, pv.y)));
        }
#pragma unroll
        for (int i = 0; i < 8; i += 2) stmatrix4((trow ^ (i << 4)) + hf * 16384, x[2 * i], x[2 * i + 1], x[2 * i + 2], x[2 * i + 3]);
      }
      if (!cand) fence_async_smem();
      __syncwarp();
      if (!cand && elect_one()) {
        tma2d_store(&maps.out, res + warp * 2048, cj * 128, rb * 128 + warp * 16);
        tma2d_store(&maps.out, res + 16384 + warp * 2048, cj * 128 + 64, rb * 128 + warp * 16);
        asm volatile("cp.async.bulk.commit_group;" ::: "memory");
      }
    }
    if (cand) {
      const int wrow0 = warp * 16;
#pragma unroll 2
      for (int p = 0; p < 8; p++) {
        const int row = 2 * p + (ln >> 4), ch = ln & 15;
        const uint4 v = lds4(res + (ch >> 3) * 16384 + (wrow0 + row) * 128 + (((ch & 7) ^ (row & 7)) << 4));
        if (rb * 128 + wrow0 + row != iwin) *reinterpret_cast<uint4*>(P.out + (size_t)(rb * 128 + wrow0 + row) * DM + cj * 128 + ch * 8) = v;
      }
    }
    asm volatile("cp.async.bulk.wait_group.read 0;" ::: "memory");
    PROF(8, ct == PT, 11); STAMP(15);
    cluster_wait();
  }
}

typedef CUresult (*EncodeFn)(CUtensorMap*, CUtensorMapDataType, cuuint32_t, void*, const cuuint64_t*, const cuuint64_t*,
                             const cuuint32_t*, const cuuint32_t*, CUtensorMapInterleave, CUtensorMapSwizzle,
                             CUtensorMapL2promotion, CUtensorMapFloatOOBfill);

void map2d(EncodeFn enc, CUtensorMap* m, const void* p, uint64_t rows, uint64_t cols, uint32_t brows) {
  cuuint64_t dims[2] = {cols, rows}, strides[1] = {cols * 2};
  cuuint32_t box[2] = {64, brows}, es[2] = {1, 1};
  enc(m, CU_TENSOR_MAP_DATA_TYPE_BFLOAT16, 2, const_cast<void*>(p), dims, strides, box, es, CU_TENSOR_MAP_INTERLEAVE_NONE,
      CU_TENSOR_MAP_SWIZZLE_128B, CU_TENSOR_MAP_L2_PROMOTION_L2_256B, CU_TENSOR_MAP_FLOAT_OOB_FILL_NONE);
}
void map2d_narrow(EncodeFn enc, CUtensorMap* m, const void* p, uint64_t rows, uint64_t cols, uint32_t brows) {
  cuuint64_t dims[2] = {cols, rows}, strides[1] = {cols * 2};
  cuuint32_t box[2] = {32, brows}, es[2] = {1, 1};
  enc(m, CU_TENSOR_MAP_DATA_TYPE_BFLOAT16, 2, const_cast<void*>(p), dims, strides, box, es, CU_TENSOR_MAP_INTERLEAVE_NONE,
      CU_TENSOR_MAP_SWIZZLE_64B, CU_TENSOR_MAP_L2_PROMOTION_L2_64B, CU_TENSOR_MAP_FLOAT_OOB_FILL_NONE);
}
void map3d(EncodeFn enc, CUtensorMap* m, const void* p, uint64_t rows, uint64_t cols, uint32_t brows, uint32_t nch) {
  cuuint64_t dims[3] = {64, rows, cols / 64}, strides[2] = {cols * 2, 128};
  cuuint32_t box[3] = {64, brows, nch}, es[3] = {1, 1, 1};
  enc(m, CU_TENSOR_MAP_DATA_TYPE_BFLOAT16, 3, const_cast<void*>(p), dims, strides, box, es, CU_TENSOR_MAP_INTERLEAVE_NONE,
      CU_TENSOR_MAP_SWIZZLE_128B, CU_TENSOR_MAP_L2_PROMOTION_L2_256B, CU_TENSOR_MAP_FLOAT_OOB_FILL_NONE);
}

}

extern "C" void kernel_launch(void* const* d_in, const int* in_sizes, int n_in, void* d_out, int out_size) {
  (void)in_sizes; (void)n_in; (void)out_size;
  static EncodeFn enc = nullptr;
  if (!enc) {
    void* fn = nullptr;
    cudaDriverEntryPointQueryResult st;
    cudaGetDriverEntryPoint("cuTensorMapEncodeTiled", &fn, cudaEnableDefault, &st);
    enc = (EncodeFn)fn;
    cudaFuncSetAttribute(fused_kernel, cudaFuncAttributeMaxDynamicSharedMemorySize, SMEM_BYTES);
  }
  Maps maps;
  map2d(enc, &maps.x, d_in[0], SEQ, DM, 128);
  map2d(enc, &maps.out, d_out, SEQ, DM, 16);
  map3d(enc, &maps.wq, d_in[3], DM, NQ, 64, 2);
  map3d(enc, &maps.k, d_in[1], 4 * SK, 128, 128, 1);
  map3d(enc, &maps.v, d_in[2], 4 * SK, 128, 128, 1);
  map3d(enc, &maps.wo, d_in[4], NQ, DM, 64, 2);
  map2d_narrow(enc, &maps.wg, d_in[7], DM, FF, 256);
  map2d_narrow(enc, &maps.wu, d_in[8], DM, FF, 256);
  map3d(enc, &maps.wd, d_in[9], FF, DM, 32, 4);
  map2d_narrow(enc, &maps.wm, d_in[11], DM, NMOD, 256);
  Ptrs p;
  p.x = (const __nv_bfloat16*)d_in[0];
  p.w_r = (const __nv_bfloat16*)d_in[6];
  p.w_gate = (const __nv_bfloat16*)d_in[7];
  p.w_up = (const __nv_bfloat16*)d_in[8];
  p.w_down = (const __nv_bfloat16*)d_in[9];
  p.c = (const __nv_bfloat16*)d_in[10];
  p.w_mod = (const __nv_bfloat16*)d_in[11];
  p.out = (__nv_bfloat16*)d_out;
  fused_kernel<<<NMAIN + NHELP, 384, SMEM_BYTES>>>(maps, p);
}
```

```cpp
#include <cuda_runtime.h>
#include <cuda_bf16.h>
#include <cuda.h>
#include <stdint.h>
#include <type_traits>

#define HD 2
#define HDX 2
#define NRS 8
#define FPACE 3
#define GOST 20
#define WB 2
#define WN 20
#define RES0 17
#define RES1 20
#define HU 32
#define NS1 5
#define PG0 15
#define PSL 0
#define FB0 0
#define FB2 8
#define OPS 8192
#define OFL 0
#define ODS 8
#define MODUL hfma2
#define ODS1 5
#define LD1 0
#define LD2 4
#define FB1 2
#define FPB 8
#define FPACE0 2
#define HALFW 1
#define HWB 1
#define VREL 5
#define E0 3

namespace {

constexpr int SEQ = 2048, DM = 1024, NQ = 4096, SK = 2048, WIN = 512, FF = 3584, NMOD = 6144;
constexpr int NMAIN = 128, NHELP = 4, NFFN = 112;
constexpr int NSLOT = 4, SLOT_BYTES = 32768, UNIT = 16384, GST_BYTES = 3 * UNIT;
constexpr uint32_t XT1 = 0xDCBA, XT2 = 0x9687;
constexpr uint32_t WT0 = 0xA741, WT1 = 0x7420, WT2 = 0x4A20;
constexpr uint32_t AT0 = WT1, AT1 = WT2;
constexpr uint32_t QT = 0xDC9696DC;
constexpr int OFF_STAGE = 12 * UNIT;
constexpr uint32_t FT_G = 0x07B3, FT_U = 0xA628, FT_D = 0x5149;
constexpr int OFF_RES = 12 * UNIT;
constexpr int OFF_PAR = 14 * UNIT;
constexpr int OFF_BAR = OFF_PAR + 2528;
constexpr int SMEM_BYTES = OFF_BAR + 544;
static_assert(SMEM_BYTES <= 232448, "smem");

constexpr int PAR_T1 = 0;
constexpr int PAR_T2 = 512;
constexpr int PAR_CONST = 1536;
constexpr int PAR_RED = 1600;
constexpr int PAR_SINK = 2176;

struct Maps {
  CUtensorMap x, wq, k, v, wo, wg, wu, wd, wm, out;
};
struct Ptrs {
  const __nv_bfloat16 *x, *w_r, *c, *w_mod, *w_gate, *w_up, *w_down;
  __nv_bfloat16* out;
};

__device__ __align__(1024) uint8_t g_act[16 * 80 * UNIT];
__device__ __align__(128) uint32_t g_mod[NMOD];
__device__ __align__(128) uint32_t g_modp[2 * 2 * DM];
__device__ __align__(128) uint32_t g_ln1[SEQ * 4];
__device__ __align__(128) uint32_t g_cnt_h[16 * 32];
__device__ __align__(128) uint32_t g_cnt_o[128 * 32];
__device__ __align__(128) uint32_t g_xch[NMAIN * 8 * 256 * 4];
__device__ __align__(128) uint32_t g_stats[8 * SEQ * 4];
__device__ __align__(128) uint32_t g_cand[32];
__device__ __align__(128) uint32_t g_row[16 * 2 * DM];
__device__ __align__(128) uint32_t g_ypart[NMAIN * NFFN * 8];
__device__ uint32_t g_epoch;

__device__ __forceinline__ uint32_t fresh_lane() { uint32_t l; asm volatile("mov.u32 %0, %%laneid;" : "=r"(l)); return l; }
__device__ __forceinline__ uint32_t frag_offset(int warp) {
  const uint32_t l = fresh_lane();
  return ((warp & 3) * 16 + (l & 15)) * 128 + (((l >> 4) ^ (l & 7)) << 4);
}
__device__ __forceinline__ bool elect_one() {
  uint32_t p;
  asm volatile("{ .reg .pred q; elect.sync _|q, 0xffffffff; selp.u32 %0, 1, 0, q; }" : "=r"(p));
  return p;
}
__device__ __forceinline__ uint32_t smem_u32(const void* p) { return (uint32_t)__cvta_generic_to_shared(p); }
__device__ __forceinline__ void mbar_init(uint32_t bar, uint32_t cnt) {
  asm volatile("mbarrier.init.shared::cta.b64 [%0], %1;" ::"r"(bar), "r"(cnt) : "memory");
}
__device__ __forceinline__ void mbar_expect_tx(uint32_t bar, uint32_t bytes) {
  asm volatile("mbarrier.arrive.expect_tx.shared::cta.b64 _, [%0], %1;" ::"r"(bar), "r"(bytes) : "memory");
}
__device__ __forceinline__ void mbar_arrive(uint32_t bar) {
  asm volatile("mbarrier.arrive.shared::cta.b64 _, [%0];" ::"r"(bar) : "memory");
}
__device__ __forceinline__ void mbar_arrive_pred(uint32_t bar, bool p) {
  asm volatile("{ .reg .pred p; setp.ne.b32 p, %1, 0; @p mbarrier.arrive.shared::cta.b64 _, [%0]; }" ::"r"(bar), "r"((int)p) : "memory");
}
__device__ __forceinline__ void mbar_arrive_cl(uint32_t bar, uint32_t off, bool p = true) {
  asm volatile("{ .reg .pred p, q; .reg .b32 a; setp.ne.b32 q, %2, 0; setp.ne.and.b32 p, %0, 0, q; add.u32 a, %0, %1; @p mbarrier.arrive.shared::cluster.b64 _, [a]; }"
               ::"r"(bar), "r"(off), "r"((int)p) : "memory");
}
__device__ __forceinline__ uint32_t mapa(uint32_t addr, uint32_t cta) {
  uint32_t r; asm("mapa.shared::cluster.u32 %0, %1, %2;" : "=r"(r) : "r"(addr), "r"(cta)); return r;
}
__device__ __forceinline__ void cluster_arrive() { asm volatile("barrier.cluster.arrive.relaxed.aligned;" ::: "memory"); }
__device__ __forceinline__ void cluster_wait() { asm volatile("barrier.cluster.wait.aligned;" ::: "memory"); }
__device__ __forceinline__ void watchdog(uint32_t& n) {
}
__device__ __forceinline__ void mbar_wait(uint32_t bar, uint32_t parity) {
  asm volatile("{\n.reg .pred p;\nWAIT_%=:\nmbarrier.try_wait.parity.shared::cta.b64 p, [%0], %1;\n@!p bra WAIT_%=;\n}" ::"r"(bar), "r"(parity) : "memory");
}
__device__ __forceinline__ bool mbar_test(uint32_t bar, uint32_t parity) {
  uint32_t ok;
  asm volatile("{\n.reg .pred p;\nmbarrier.test_wait.parity.shared::cta.b64 p, [%1], %2;\nselp.u32 %0, 1, 0, p;\n}" : "=r"(ok) : "r"(bar), "r"(parity) : "memory");
  return ok;
}
__device__ __forceinline__ uint64_t l2_stream() {
  uint64_t f; asm("createpolicy.fractional.L2::evict_first.b64 %0, 1.0;" : "=l"(f)); return f;
}
__device__ __forceinline__ void tma2d(uint32_t dst, const CUtensorMap* m, int c0, int c1, uint32_t bar) {
  asm volatile("cp.async.bulk.tensor.2d.shared::cluster.global.mbarrier::complete_tx::bytes.L2::cache_hint [%0], [%1, {%3, %4}], [%2], %5;"
               ::"r"(dst), "l"(m), "r"(bar), "r"(c0), "r"(c1), "l"(l2_stream()) : "memory");
}
__device__ __forceinline__ void bulk_load(uint32_t dst, const void* src, uint32_t bytes, uint32_t bar) {
  asm volatile("cp.async.bulk.shared::cluster.global.mbarrier::complete_tx::bytes [%0], [%1], %2, [%3];" ::"r"(dst), "l"(src), "r"(bytes), "r"(bar) : "memory");
}
__device__ __forceinline__ void bulk_load_stream(uint32_t dst, const void* src, uint32_t bytes, uint32_t bar) {
  asm volatile("cp.async.bulk.shared::cluster.global.mbarrier::complete_tx::bytes.L2::cache_hint [%0], [%1], %2, [%3], %4;"
               ::"r"(dst), "l"(src), "r"(bytes), "r"(bar), "l"(l2_stream()) : "memory");
}
__device__ __forceinline__ void tma2d_store(const CUtensorMap* m, uint32_t src, int c0, int c1) {
  asm volatile("cp.async.bulk.tensor.2d.global.shared::cta.bulk_group [%0, {%2, %3}], [%1];" ::"l"(m), "r"(src), "r"(c0), "r"(c1) : "memory");
}
__device__ __forceinline__ void bulk_store(void* dst, uint32_t src, uint32_t bytes) {
  asm volatile("cp.async.bulk.global.shared::cta.bulk_group [%0], [%1], %2;" ::"l"(dst), "r"(src), "r"(bytes) : "memory");
}
__device__ __forceinline__ int slice_of(int i) { return HALFW ? i + ((i & 7) == 1) - ((i & 7) == 2) : i; }
__device__ __forceinline__ uint32_t unit_of(uint32_t table, uint32_t i) { return ((table >> (i * 4)) & 15) * UNIT; }
__device__ __forceinline__ void tma3d(uint32_t dst, const CUtensorMap* m, int c0, int c1, int c2, uint32_t bar) {
  asm volatile("cp.async.bulk.tensor.3d.shared::cluster.global.mbarrier::complete_tx::bytes.L2::cache_hint [%0], [%1, {%3, %4, %5}], [%2], %6;"
               ::"r"(dst), "l"(m), "r"(bar), "r"(c0), "r"(c1), "r"(c2), "l"(l2_stream()) : "memory");
}
template <bool STREAM>
__device__ __forceinline__ void tma3d_mc(uint32_t dst, const CUtensorMap* m, int c0, int c1, int c2, uint32_t bar) {
  if (STREAM)
    asm volatile("cp.async.bulk.tensor.3d.shared::cluster.global.mbarrier::complete_tx::bytes.multicast::cluster.L2::cache_hint [%0], [%1, {%3, %4, %5}], [%2], %6, %7;"
                 ::"r"(dst), "l"(m), "r"(bar), "r"(c0), "r"(c1), "r"(c2), "h"((uint16_t)3), "l"(l2_stream()) : "memory");
  else
    asm volatile("cp.async.bulk.tensor.3d.shared::cluster.global.mbarrier::complete_tx::bytes.multicast::cluster [%0], [%1, {%3, %4, %5}], [%2], %6;"
                 ::"r"(dst), "l"(m), "r"(bar), "r"(c0), "r"(c1), "r"(c2), "h"((uint16_t)3) : "memory");
}
__device__ __forceinline__ void prefetch_map(const CUtensorMap* m) {
  asm volatile("prefetch.tensormap [%0];" ::"l"(m) : "memory");
}
__device__ __forceinline__ void fence_async() { asm volatile("fence.proxy.async.global;" ::: "memory"); }
__device__ __forceinline__ void fence_async_smem() { asm volatile("fence.proxy.async.shared::cta;" ::: "memory"); }
__device__ __forceinline__ void bar_sync(int id, int n) { asm volatile("bar.sync %0, %1;" ::"r"(id), "r"(n) : "memory"); }
__device__ __forceinline__ void bar_arrive(int id, int n) { asm volatile("bar.arrive %0, %1;" ::"r"(id), "r"(n) : "memory"); }
__device__ __forceinline__ void wg_fence() { asm volatile("wgmma.fence.sync.aligned;" ::: "memory"); }
__device__ __forceinline__ void wg_commit() { asm volatile("wgmma.commit_group.sync.aligned;" ::: "memory"); }
template <int N> __device__ __forceinline__ void wg_wait() { asm volatile("wgmma.wait_group.sync.aligned %0;" ::"n"(N) : "memory"); }
__device__ __forceinline__ uint64_t make_desc(uint32_t addr, uint32_t lbo, uint32_t sbo) {
  return (uint64_t)((addr & 0x3FFFF) >> 4) | ((uint64_t)(lbo >> 4) << 16) | ((uint64_t)(sbo >> 4) << 32) | (1ull << 62);
}
__device__ __forceinline__ uint32_t ld_relaxed(const uint32_t* p) {
  uint32_t v; asm volatile("ld.relaxed.gpu.global.u32 %0, [%1];" : "=r"(v) : "l"(p) : "memory"); return v;
}
__device__ __forceinline__ uint32_t ld_acquire(const uint32_t* p) {
  uint32_t v; asm volatile("ld.acquire.gpu.global.u32 %0, [%1];" : "=r"(v) : "l"(p) : "memory"); return v;
}
__device__ __forceinline__ uint4 ld_relaxed4(const uint32_t* p) {
  uint4 v; asm volatile("ld.relaxed.gpu.global.v4.u32 {%0,%1,%2,%3}, [%4];" : "=r"(v.x), "=r"(v.y), "=r"(v.z), "=r"(v.w) : "l"(p) : "memory"); return v;
}
__device__ __forceinline__ uint2 ld_relaxed2(const uint32_t* p) {
  uint2 v; asm volatile("ld.relaxed.gpu.global.v2.u32 {%0,%1}, [%2];" : "=r"(v.x), "=r"(v.y) : "l"(p) : "memory"); return v;
}
__device__ __forceinline__ void st_relaxed(uint32_t* p, uint32_t v) {
  asm volatile("st.relaxed.gpu.global.u32 [%0], %1;" ::"l"(p), "r"(v) : "memory");
}
__device__ __forceinline__ void st_relaxed2(uint32_t* p, uint32_t a, uint32_t b) {
  asm volatile("st.relaxed.gpu.global.v2.u32 [%0], {%1,%2};" ::"l"(p), "r"(a), "r"(b) : "memory");
}
__device__ __forceinline__ void st_relaxed4(uint32_t* p, uint32_t a, uint32_t b, uint32_t c, uint32_t d) {
  asm volatile("st.relaxed.gpu.global.v4.u32 [%0], {%1,%2,%3,%4};" ::"l"(p), "r"(a), "r"(b), "r"(c), "r"(d) : "memory");
}
__device__ __forceinline__ void st_b128(uint32_t* p, uint32_t a, uint32_t b, uint32_t c, uint32_t d) {
  asm volatile("{ .reg .b64 u, v; .reg .b128 w; mov.b64 u, {%1, %2}; mov.b64 v, {%3, %4}; mov.b128 w, {u, v}; st.relaxed.gpu.global.b128 [%0], w; }"
               ::"l"(p), "r"(a), "r"(b), "r"(c), "r"(d) : "memory");
}
__device__ __forceinline__ uint4 ld_b128(const uint32_t* p) {
  uint4 r;
  asm volatile("{ .reg .b64 u, v; .reg .b128 w; ld.relaxed.gpu.global.b128 w, [%4]; mov.b128 {u, v}, w; mov.b64 {%0, %1}, u; mov.b64 {%2, %3}, v; }"
               : "=r"(r.x), "=r"(r.y), "=r"(r.z), "=r"(r.w) : "l"(p) : "memory");
  return r;
}
__device__ __forceinline__ void st_pairs(uint32_t* p, uint32_t a, uint32_t b, uint32_t tag) {
  asm volatile("{ .reg .b64 u, v; mov.b64 u, {%1, %3}; mov.b64 v, {%2, %3}; st.relaxed.gpu.global.v2.b64 [%0], {u, v}; }"
               ::"l"(p), "r"(a), "r"(b), "r"(tag) : "memory");
}
__device__ __forceinline__ uint4 ld_pairs(const uint32_t* p) {
  uint4 v;
  asm volatile("{ .reg .b64 u, v; ld.relaxed.gpu.global.v2.b64 {u, v}, [%4]; mov.b64 {%0, %1}, u; mov.b64 {%2, %3}, v; }"
               : "=r"(v.x), "=r"(v.y), "=r"(v.z), "=r"(v.w) : "l"(p) : "memory");
  return v;
}
__device__ __forceinline__ uint2 ld_pair(const uint32_t* p) {
  uint2 v;
  asm volatile("{ .reg .b64 u; ld.relaxed.gpu.global.b64 u, [%2]; mov.b64 {%0, %1}, u; }" : "=r"(v.x), "=r"(v.y) : "l"(p) : "memory");
  return v;
}
__device__ __forceinline__ void red_release(uint32_t* p, uint32_t v) {
  asm volatile("red.release.gpu.global.add.u32 [%0], %1;" ::"l"(p), "r"(v) : "memory");
}
__device__ __forceinline__ uint32_t ldg_nc1(const void* p) {
  uint32_t v;
  asm volatile("ld.global.nc.u32 %0, [%1];" : "=r"(v) : "l"(p));
  return v;
}
__device__ __forceinline__ uint4 ldg_nc4(const void* p) {
  uint4 v; asm volatile("ld.global.nc.L1::no_allocate.v4.u32 {%0,%1,%2,%3}, [%4];" : "=r"(v.x), "=r"(v.y), "=r"(v.z), "=r"(v.w) : "l"(p)); return v;
}
__device__ __forceinline__ uint4 ldg_stream4(const void* p) {
  uint4 v;
  asm volatile("ld.global.nc.L1::no_allocate.L2::cache_hint.v4.u32 {%0,%1,%2,%3}, [%4], %5;" : "=r"(v.x), "=r"(v.y), "=r"(v.z), "=r"(v.w) : "l"(p), "l"(l2_stream()));
  return v;
}
__device__ __forceinline__ void stg4(void* p, uint4 v) {
  asm volatile("st.global.v4.u32 [%0], {%1,%2,%3,%4};" ::"l"(p), "r"(v.x), "r"(v.y), "r"(v.z), "r"(v.w) : "memory");
}
__device__ __forceinline__ void wait_counter(const uint32_t* p, uint32_t target) {
  uint32_t n = 0;
  while (__any_sync(0xffffffffu, (int)(ld_acquire(p) - target) < 0)) { watchdog(n); }
}
__device__ __forceinline__ uint32_t tagf(float v, uint32_t tag) { return (__float_as_uint(v) & ~3u) | tag; }
__device__ __forceinline__ bool tag_ok(uint4 v, uint32_t tag) { return (((v.x ^ tag) | (v.y ^ tag) | (v.z ^ tag) | (v.w ^ tag)) & 3u) == 0; }
__device__ __forceinline__ float untag_sum(uint32_t a, uint32_t b) { return __uint_as_float(a & ~3u) + __uint_as_float(b & ~3u); }
__device__ __forceinline__ uint4 poll4(const uint32_t* p, uint32_t tag) {
  uint4 v = ld_relaxed4(p);
  uint32_t n = 0;
  while (!__all_sync(0xffffffffu, tag_ok(v, tag))) { v = ld_relaxed4(p); watchdog(n); }
  return v;
}
__device__ __forceinline__ float bf_lo(uint32_t v) { return __uint_as_float(v << 16); }
__device__ __forceinline__ float bf_hi(uint32_t v) { return __uint_as_float(v & 0xffff0000u); }
__device__ __forceinline__ uint32_t pack_bf(float lo, float hi) {
  uint32_t r; asm("cvt.rn.bf16x2.f32 %0, %1, %2;" : "=r"(r) : "f"(hi), "f"(lo)); return r;
}
__device__ __forceinline__ float rbf(float v) { return __uint_as_float(pack_bf(0.f, v) & 0xffff0000u); }
__device__ __forceinline__ uint32_t hmul2(uint32_t a, uint32_t b) {
  uint32_t r; asm("mul.rn.bf16x2 %0, %1, %2;" : "=r"(r) : "r"(a), "r"(b)); return r;
}
__device__ __forceinline__ uint32_t hadd2(uint32_t a, uint32_t b) {
  uint32_t r; asm("add.rn.bf16x2 %0, %1, %2;" : "=r"(r) : "r"(a), "r"(b)); return r;
}
__device__ __forceinline__ uint32_t hsub2(uint32_t a, uint32_t b) {
  uint32_t r; asm("sub.rn.bf16x2 %0, %1, %2;" : "=r"(r) : "r"(a), "r"(b)); return r;
}
__device__ __forceinline__ uint32_t hmax2(uint32_t a, uint32_t b) {
  uint32_t r; asm("max.bf16x2 %0, %1, %2;" : "=r"(r) : "r"(a), "r"(b)); return r;
}
__device__ __forceinline__ float rcp(float x) { float r; asm("rcp.approx.ftz.f32 %0, %1;" : "=f"(r) : "f"(x)); return r; }
__device__ __forceinline__ float ex2(float x) { float r; asm("ex2.approx.ftz.f32 %0, %1;" : "=f"(r) : "f"(x)); return r; }
__device__ __forceinline__ void stmatrix4(uint32_t addr, uint32_t a, uint32_t b, uint32_t c, uint32_t d) {
  asm volatile("stmatrix.sync.aligned.m8n8.x4.shared.b16 [%0], {%1,%2,%3,%4};" ::"r"(addr), "r"(a), "r"(b), "r"(c), "r"(d) : "memory");
}
__device__ __forceinline__ void ldmatrix4(uint32_t addr, uint32_t& a, uint32_t& b, uint32_t& c, uint32_t& d) {
  asm volatile("ldmatrix.sync.aligned.m8n8.x4.shared.b16 {%0,%1,%2,%3}, [%4];" : "=r"(a), "=r"(b), "=r"(c), "=r"(d) : "r"(addr) : "memory");
}
__device__ __forceinline__ void ldmatrix4t(uint32_t addr, uint32_t& a, uint32_t& b, uint32_t& c, uint32_t& d) {
  asm volatile("ldmatrix.sync.aligned.m8n8.x4.trans.shared.b16 {%0,%1,%2,%3}, [%4];" : "=r"(a), "=r"(b), "=r"(c), "=r"(d) : "r"(addr) : "memory");
}
__device__ __forceinline__ void mma16816(float (&d)[4], uint32_t a0, uint32_t a1, uint32_t a2, uint32_t a3, uint32_t b0, uint32_t b1) {
  asm volatile("mma.sync.aligned.m16n8k16.row.col.f32.bf16.bf16.f32 {%0,%1,%2,%3}, {%4,%5,%6,%7}, {%8,%9}, {%0,%1,%2,%3};"
               : "+f"(d[0]), "+f"(d[1]), "+f"(d[2]), "+f"(d[3]) : "r"(a0), "r"(a1), "r"(a2), "r"(a3), "r"(b0), "r"(b1));
}
__device__ __forceinline__ void sts1(uint32_t a, uint32_t v) { asm volatile("st.shared.u32 [%0], %1;" ::"r"(a), "r"(v) : "memory"); }
__device__ __forceinline__ uint4 lds4(uint32_t a) {
  uint4 v; asm volatile("ld.shared.v4.u32 {%0,%1,%2,%3}, [%4];" : "=r"(v.x), "=r"(v.y), "=r"(v.z), "=r"(v.w) : "r"(a) : "memory"); return v;
}
__device__ __forceinline__ uint2 lds2(uint32_t a) {
  uint2 v; asm volatile("ld.shared.v2.u32 {%0,%1}, [%2];" : "=r"(v.x), "=r"(v.y) : "r"(a) : "memory"); return v;
}
__device__ __forceinline__ uint32_t lds1(uint32_t a) {
  uint32_t v; asm volatile("ld.shared.u32 %0, [%1];" : "=r"(v) : "r"(a) : "memory"); return v;
}
__device__ __forceinline__ void sts2(uint32_t a, uint32_t x, uint32_t y) { asm volatile("st.shared.v2.u32 [%0], {%1,%2};" ::"r"(a), "r"(x), "r"(y) : "memory"); }
__device__ __forceinline__ void sts4(uint32_t a, uint4 v) {
  asm volatile("st.shared.v4.u32 [%0], {%1,%2,%3,%4};" ::"r"(a), "r"(v.x), "r"(v.y), "r"(v.z), "r"(v.w) : "memory");
}
__device__ __forceinline__ float silu_f(float v) { return __fdividef(v, 1.f + __expf(-v)); }
__device__ __forceinline__ uint32_t hfma2(uint32_t a, uint32_t b, uint32_t c) {
  uint32_t r; asm("fma.rn.bf16x2 %0, %1, %2, %3;" : "=r"(r) : "r"(a), "r"(b), "r"(c)); return r;
}
__device__ __forceinline__ void split_inv(float sd, uint32_t& ih, uint32_t& il) {
  const float inv = rcp(sd);
  ih = pack_bf(inv, inv);
  const float lo = inv - bf_lo(ih);
  il = pack_bf(lo, lo);
}
__device__ __forceinline__ uint32_t ln_norm(uint32_t x, uint32_t mean2, uint32_t ih, uint32_t il) {
  const uint32_t d = hsub2(x, mean2);
  return hfma2(d, ih, hmul2(d, il));
}
__device__ __forceinline__ uint32_t modul(uint32_t n, uint32_t c1, uint32_t sh) { return hadd2(hmul2(n, c1), sh); }
__device__ __forceinline__ uint32_t ln_mod(uint32_t x, uint32_t mean2, uint32_t ih, uint32_t il, uint32_t c1, uint32_t sh) {
  return modul(ln_norm(x, mean2, ih, il), c1, sh);
}

#define R8(a, i) "+f"(a[i]), "+f"(a[i + 1]), "+f"(a[i + 2]), "+f"(a[i + 3]), "+f"(a[i + 4]), "+f"(a[i + 5]), "+f"(a[i + 6]), "+f"(a[i + 7])
#define D64 "{%0,%1,%2,%3,%4,%5,%6,%7,%8,%9,%10,%11,%12,%13,%14,%15,%16,%17,%18,%19,%20,%21,%22,%23,%24,%25,%26,%27,%28,%29,%30,%31," \
            "%32,%33,%34,%35,%36,%37,%38,%39,%40,%41,%42,%43,%44,%45,%46,%47,%48,%49,%50,%51,%52,%53,%54,%55,%56,%57,%58,%59,%60,%61,%62,%63}"
template <int TB>
__device__ __forceinline__ void mma_ss(float (&d)[64], uint64_t da, uint64_t db, int sc) {
  asm volatile("{\n.reg .pred p;\nsetp.ne.b32 p, %66, 0;\n"
               "wgmma.mma_async.sync.aligned.m64n128k16.f32.bf16.bf16 " D64 ", %64, %65, p, 1, 1, 0, %67;\n}"
               : R8(d, 0), R8(d, 8), R8(d, 16), R8(d, 24), R8(d, 32), R8(d, 40), R8(d, 48), R8(d, 56)
               : "l"(da), "l"(db), "r"(sc), "n"(TB));
}
template <int TB>
__device__ __forceinline__ void mma_rs(float (&d)[64], uint32_t a0, uint32_t a1, uint32_t a2, uint32_t a3, uint64_t db, int sc) {
  asm volatile("{\n.reg .pred p;\nsetp.ne.b32 p, %69, 0;\n"
               "wgmma.mma_async.sync.aligned.m64n128k16.f32.bf16.bf16 " D64 ", {%64,%65,%66,%67}, %68, p, 1, 1, %70;\n}"
               : R8(d, 0), R8(d, 8), R8(d, 16), R8(d, 24), R8(d, 32), R8(d, 40), R8(d, 48), R8(d, 56)
               : "r"(a0), "r"(a1), "r"(a2), "r"(a3), "l"(db), "r"(sc), "n"(TB));
}
#define D128 "{%0,%1,%2,%3,%4,%5,%6,%7,%8,%9,%10,%11,%12,%13,%14,%15,%16,%17,%18,%19,%20,%21,%22,%23,%24,%25,%26,%27,%28,%29,%30,%31," \
             "%32,%33,%34,%35,%36,%37,%38,%39,%40,%41,%42,%43,%44,%45,%46,%47,%48,%49,%50,%51,%52,%53,%54,%55,%56,%57,%58,%59,%60,%61,%62,%63," \
             "%64,%65,%66,%67,%68,%69,%70,%71,%72,%73,%74,%75,%76,%77,%78,%79,%80,%81,%82,%83,%84,%85,%86,%87,%88,%89,%90,%91,%92,%93,%94,%95," \
             "%96,%97,%98,%99,%100,%101,%102,%103,%104,%105,%106,%107,%108,%109,%110,%111,%112,%113,%114,%115,%116,%117,%118,%119,%120,%121,%122,%123,%124,%125,%126,%127}"
#define R128(d, e) R8(d, 0), R8(d, 8), R8(d, 16), R8(d, 24), R8(d, 32), R8(d, 40), R8(d, 48), R8(d, 56), \
                   R8(e, 0), R8(e, 8), R8(e, 16), R8(e, 24), R8(e, 32), R8(e, 40), R8(e, 48), R8(e, 56)
__device__ __forceinline__ void mma256_ss(float (&d)[64], float (&e)[64], uint64_t da, uint64_t db, int sc) {
  asm volatile("{\n.reg .pred p;\nsetp.ne.b32 p, %130, 0;\n"
               "wgmma.mma_async.sync.aligned.m64n256k16.f32.bf16.bf16 " D128 ", %128, %129, p, 1, 1, 0, 1;\n}"
               : R128(d, e) : "l"(da), "l"(db), "r"(sc));
}
__device__ __forceinline__ void mma256_rs(float (&d)[64], float (&e)[64], uint32_t a0, uint32_t a1, uint32_t a2, uint32_t a3, uint64_t db) {
  asm volatile("{\n.reg .pred p;\nsetp.ne.b32 p, 1, 0;\n"
               "wgmma.mma_async.sync.aligned.m64n256k16.f32.bf16.bf16 " D128 ", {%128,%129,%130,%131}, %132, p, 1, 1, 1;\n}"
               : R128(d, e) : "r"(a0), "r"(a1), "r"(a2), "r"(a3), "l"(db));
}
template <int N> __device__ __forceinline__ void keep(float (&a)[N]) {
#pragma unroll
  for (int i = 0; i < N; i++) asm volatile("" : "+f"(a[i])::"memory");
}
template <int N> __device__ __forceinline__ void keep(uint32_t (&a)[N]) {
#pragma unroll
  for (int i = 0; i < N; i++) asm volatile("" : "+r"(a[i])::"memory");
}

#define STAMP(idx) do {} while (0)
#define PROF(grp, cond, idx) do {} while (0)

constexpr float SCL2 = 1.4426950408889634f * 0.08838834764831845f;

__device__ __forceinline__ void pack_p(const float (&s)[64], uint32_t (&p)[32]) {
#pragma unroll
  for (int i = 0; i < 32; i++) p[i] = pack_bf(s[2 * i], s[2 * i + 1]);
}

__device__ __forceinline__ void issue_qk(float (&s)[64], uint32_t q0, uint32_t q1, uint32_t kslot) {
  const uint64_t db = make_desc(kslot, 16, 1024), da0 = make_desc(q0, 16, 1024), da1 = make_desc(q1, 16, 1024);
#pragma unroll
  for (int kk = 0; kk < 8; kk++) mma_ss<0>(s, (kk < 4 ? da0 : da1) + (kk & 3) * 2, db + (kk >> 2) * 1024 + (kk & 3) * 2, kk != 0);
}
__device__ __forceinline__ void issue_pv(float (&o)[64], uint32_t (&p)[32], uint32_t vslot, int acc) {
  uint64_t db = make_desc(vslot, 16384, 1024);
#pragma unroll
  for (int kk = 0; kk < 8; kk++)
    mma_rs<1>(o, p[4 * kk], p[4 * kk + 1], p[4 * kk + 2], p[4 * kk + 3], db + kk * 128, kk == 0 ? acc : 1);
}

template <int H>
__device__ __forceinline__ void store_chunk(const float (&a)[64], uint32_t addr) {
#pragma unroll
  for (int i = 8 * H; i < 8 * H + 8; i += 2)
    stmatrix4(addr ^ ((i & 7) << 4), pack_bf(a[4 * i], a[4 * i + 1]), pack_bf(a[4 * i + 2], a[4 * i + 3]),
              pack_bf(a[4 * i + 4], a[4 * i + 5]), pack_bf(a[4 * i + 6], a[4 * i + 7]));
}
template <int H>
__device__ __forceinline__ void store_chunk(const float (&a)[64], float i0, float i1, uint32_t addr) {
#pragma unroll
  for (int i = 8 * H; i < 8 * H + 8; i += 2)
    stmatrix4(addr ^ ((i & 7) << 4), pack_bf(a[4 * i] * i0, a[4 * i + 1] * i0), pack_bf(a[4 * i + 2] * i1, a[4 * i + 3] * i1),
              pack_bf(a[4 * i + 4] * i0, a[4 * i + 5] * i0), pack_bf(a[4 * i + 6] * i1, a[4 * i + 7] * i1));
}
__device__ __forceinline__ float inv_quad_sum(float l) {
  l += __shfl_xor_sync(0xffffffffu, l, 1);
  l += __shfl_xor_sync(0xffffffffu, l, 2);
  return rcp(l);
}

__device__ __forceinline__ void ln_scalars(float mean, float var, float& mb, float& sd) {
  mb = rbf(mean);
  float r; asm("sqrt.approx.ftz.f32 %0, %1;" : "=f"(r) : "f"(rbf(rbf(var) + 1e-5f)));
  sd = rbf(r);
}

__global__ void __cluster_dims__(2, 1, 1) __launch_bounds__(384, 1) fused_kernel(const __grid_constant__ Maps maps, const Ptrs P) {
  extern __shared__ __align__(1024) uint8_t smem_raw[];
  const uint32_t base = smem_u32(smem_raw);
  const int tid = threadIdx.x, lane = tid & 31;
  const int warp = __shfl_sync(0xffffffffu, tid >> 5, 0);
  const int b = blockIdx.x;
  PROF(31, tid == 0, 0);

  if (b >= NMAIN) {
    float* sc = reinterpret_cast<float*>(smem_raw);
    float* red = sc + DM;
    for (int k = tid; k < DM; k += 384) sc[k] = rbf(silu_f(__bfloat162float(P.c[k])));
    __syncthreads();
    if (tid < 256) {
      const int col = 2048 + (b - NMAIN) * 1024 + (tid & 127) * 8, r0 = (tid >> 7) * 512;
      float acc[8];
#pragma unroll
      for (int e = 0; e < 8; e++) acc[e] = 0.f;
#pragma unroll 1
      for (int r = r0; r < r0 + 512; r += HU) {
        uint4 w[HU];
#pragma unroll
        for (int u = 0; u < HU; u++) w[u] = ldg_stream4(P.w_mod + (size_t)(r + u) * NMOD + col);
#pragma unroll
        for (int u = 0; u < HU; u++) {
          float s = sc[r + u];
          acc[0] += s * bf_lo(w[u].x); acc[1] += s * bf_hi(w[u].x); acc[2] += s * bf_lo(w[u].y); acc[3] += s * bf_hi(w[u].y);
          acc[4] += s * bf_lo(w[u].z); acc[5] += s * bf_hi(w[u].z); acc[6] += s * bf_lo(w[u].w); acc[7] += s * bf_hi(w[u].w);
        }
      }
      if (tid >= 128) {
#pragma unroll
        for (int e = 0; e < 8; e++) red[(tid & 127) * 8 + e] = acc[e];
      }
      const uint32_t tag = ld_relaxed(&g_epoch) % 3 + 1;
      bar_sync(1, 256);
      if (tid < 128) {
        uint32_t o[8];
#pragma unroll
        for (int e = 0; e < 8; e++) o[e] = __float_as_uint(rbf(acc[e] + red[tid * 8 + e])) | tag;
        st_relaxed4(g_mod + col, o[0], o[1], o[2], o[3]);
        st_relaxed4(g_mod + col + 4, o[4], o[5], o[6], o[7]);
        const uint4 wr = ldg_nc4(P.w_r + tid * 8);
        const uint32_t wv[4] = {wr.x, wr.y, wr.z, wr.w};
        float dsum = 0.f;
#pragma unroll
        for (int e = 0; e < 8; e++) {
          const float m = bf_hi(o[e]);
          dsum += (b == NMAIN + 2 ? rbf(1.f + m) : m) * ((e & 1) ? bf_hi(wv[e >> 1]) : bf_lo(wv[e >> 1]));
        }
#pragma unroll
        for (int k = 16; k > 0; k >>= 1) dsum += __shfl_xor_sync(0xffffffffu, dsum, k);
        if (lane == 0) st_relaxed(g_mod + (b - NMAIN) * 4 + warp, tagf(dsum, tag));
      }
    }
    PROF(2, tid == 0, 1);
    return;
  }

  const int rank = b & 1;
  const int rb = ((b >> 4) << 1) | rank, cj = (b >> 1) & 7;
  const bool late = HALFW && (b & 4);
  const uint32_t bfull = base + OFF_BAR, bempty = bfull + NSLOT * 8;
  const uint32_t gfull = bempty + NSLOT * 8, gempty = gfull + 32;
  const uint32_t bar_ofull = gempty + 32;
  const uint32_t bar_ofree = bar_ofull + 32;
  const uint32_t bar_par = bar_ofree + 32;
  const uint32_t bar_mod = bar_par + 8;
  const uint32_t bar_pread = bar_mod + 8;
  const uint32_t bar_xres = bar_pread + 8;
  const uint32_t bar_ring = bar_xres + 8;
  const uint32_t bar_box = bar_ring + 24;
  const uint32_t bar_go = bar_box + 96;
  const uint32_t bar_go2 = bar_go + 16;
  const uint32_t bar_cnt = bar_go + 24;
  const uint32_t xfull = bar_go + 40, xempty = xfull + 32;
  const uint32_t bar_hw = xempty + 32, bar_hx = bar_hw + 8;
  const uint32_t bar_hpub = bar_hx + 16;
  const uint32_t bar_win = bar_hpub + 16;
  const uint32_t bar_rx = bar_win + 8;
  const uint32_t bar_sel = bar_rx + 8;
  const uint32_t bar_gate = bar_sel + 8;
  const uint32_t bar_rel = bar_gate + 8;
  const uint32_t bar_od = bar_rel + 8;
  const uint32_t bar_mod2 = bar_od + 8;
  const uint32_t bar_res = bar_go + 8;
  const uint32_t stage = base + OFF_STAGE, par = base + OFF_PAR;

  if (warp == 8 && elect_one()) {
    for (int s = 0; s < NSLOT; s++) { mbar_init(bfull + s * 8, 1); mbar_init(bempty + s * 8, 16); }
    for (int s = 0; s < 4; s++) { mbar_init(gfull + s * 8, 1); mbar_init(gempty + s * 8, 16); mbar_init(xfull + s * 8, 1); mbar_init(xempty + s * 8, 8); mbar_init(bar_ofree + s * 8, 1); mbar_init(bar_ofull + s * 8, 128); }
    mbar_init(bar_par, 64); mbar_init(bar_mod, 256); mbar_init(bar_pread, 2); mbar_init(bar_xres, 1);
    mbar_init(bar_ring, 8); mbar_init(bar_ring + 8, 8); mbar_init(bar_ring + 16, 8);
    mbar_init(bar_go, 1); mbar_init(bar_go2, 1); mbar_init(bar_cnt, 1); mbar_init(bar_cnt + 8, 1); mbar_init(bar_hpub, 8); mbar_init(bar_hpub + 8, 8); mbar_init(bar_res, 1); mbar_init(bar_win, 1); mbar_init(bar_rx, 1); mbar_init(bar_sel, 64); mbar_init(bar_gate, 8); mbar_init(bar_rel, 8); mbar_init(bar_od, 1); mbar_init(bar_mod2, 128);
    for (int s = 0; s < 12; s++) mbar_init(bar_box + s * 8, 1);
    asm volatile("fence.mbarrier_init.release.cluster;" ::: "memory");
    prefetch_map(&maps.x); prefetch_map(&maps.wq); prefetch_map(&maps.k); prefetch_map(&maps.v);
  }
  if (warp == 9 && elect_one()) {
    mbar_init(bar_hw, 1); mbar_init(bar_hx, 1); mbar_init(bar_hx + 8, 1);
    asm volatile("fence.mbarrier_init.release.cluster;" ::: "memory");
    mbar_expect_tx(bar_hw, 32768);
    mbar_expect_tx(bar_hx, 16384);
    mbar_expect_tx(bar_hx + 8, 16384);
    const __nv_bfloat16* xs = P.x + (size_t)(rb * 128 + cj * 16) * DM;
    bulk_load(base + 2 * GST_BYTES, xs, 16384, bar_hx);
    if (!late) {
      tma2d(stage, &maps.wm, (b >> 1) * 32, rank * 512, bar_hw);
      tma2d(stage + 16384, &maps.wm, (b >> 1) * 32, rank * 512 + 256, bar_hw);
    } else {
      prefetch_map(&maps.wm);
    }
    bulk_load(base + 3 * GST_BYTES, xs + 8 * DM, 16384, bar_hx + 8);
  }
  cluster_arrive();

  if (warp >= 8) {
    asm volatile("setmaxnreg.dec.sync.aligned.u32 40;");
    if (warp < 10) bar_arrive(1, 320);
    const uint32_t epoch = ld_relaxed(&g_epoch);
    cluster_wait();
    if (warp == 8) {
      const int kvrow = (cj >> 1) * SK + (SK - WIN);
      int wch = cj * 8 + rank * 2;
#pragma unroll 1
      for (int ps = 0; ps < 3; ps++) {
        const CUtensorMap* mw = ps == 2 ? &maps.wo : &maps.wq;
        const uint32_t xt = ps == 1 ? XT1 : XT2, wt = ps == 0 ? WT0 : (ps == 1 ? WT1 : WT2);
        const int nst = ps == 2 ? 32 : 16;
#pragma unroll 1
        for (int i = 0; i < nst; i++) {
          const uint32_t bf = gfull + (i & 3) * 8;
          const int kt = ps == 2 ? (((cj & 1) * 4 + ((i >> 1) & 3)) * 4 + (i >> 3)) * 2 + (i & 1) : (ps ? i : slice_of(i) + (b & 14)) & 15;
          const uint32_t wd = base + unit_of(wt, i & 3) + rank * UNIT, xd = base + unit_of(xt, i & 3);
          const uint8_t* xs = g_act + (uint32_t)(rb * 80 + (ps - 1) * 16 + kt) * UNIT;
          if (ps == 0 && i == HD) mbar_wait(bar_mod, 0);
          const bool xfirst = ps && i < 2;
          if (ps == 2 && i == 0) mbar_wait(bar_ofree + 24, 0);
          if (i == 0) fence_async();
          mbar_wait(gempty + (i & 3) * 8, ((i >> 2) & 1) ^ 1);
          if (elect_one()) {
            mbar_expect_tx(bf, ps ? GST_BYTES : 2 * UNIT);
            if (xfirst) bulk_load_stream(xd, xs, UNIT, bf);
          }
          if (ps && i < 4) mbar_wait(bempty + i * 8, 1);
          if (elect_one()) tma3d_mc<true>(wd, mw, 0, (i == 31 ? kt ^ (rank * 32) : kt) * 64, i == 31 ? cj * 2 : wch, bf);
          if (ps) {
            if (i == 16 || i == 24) { mbar_wait(bar_cnt + i - 16, 0); fence_async(); }
            if (i == RES0) mbar_wait(bar_res, 0);
            if (i == 2) mbar_wait(bar_ofree + (ps - 1) * 16, 0);
            if (elect_one()) {
              if (i == 31) bulk_load(xd, xs, UNIT, bf); else if (!xfirst) bulk_load_stream(xd, xs, UNIT, bf);
              mbar_arrive_pred(bar_go, i == GOST - 1);
              if (PG0 < 16) mbar_arrive_pred(bar_go2, ps == 1 && i == PG0);
              mbar_arrive_pred(bar_od, i == (ps == 1 ? ODS1 : ODS));
              if (i == RES0) mbar_expect_tx(bar_xres, 32768);
              if (i == RES0 || i == RES1) tma2d(base + OFF_RES + (i == RES1) * UNIT, &maps.x, cj * 128 + (i == RES1) * 64, rb * 128, bar_xres);
            }
          }
        }
        if (ps == 2) break;
        wch = ps ? ((wch >> 3) ^ rank) * 2 : wch + 4;
#pragma unroll 1
        for (int u = 0; u < 16; u++) {
          const bool isk = (u == 0) || ((u & 1) && u < 15);
          const int blk = (isk ? (u + 1) >> 1 : (u == 15 ? 7 : (u >> 1) - 1)) & 3;
          const uint32_t sl = base + unit_of(ps ? AT1 : AT0, u & 3) + rank * UNIT, bf = bfull + (u & 3) * 8;
          if (u < 4) mbar_wait(gempty + ((u + 1) >> 1) * 8, 1);
          mbar_wait(bempty + (u & 3) * 8, ((u >> 2) & 1) ^ 1);
          if (elect_one()) {
            mbar_arrive_pred(bar_go2, ps && u + 16 == PG0);
            mbar_expect_tx(bf, SLOT_BYTES);
            tma3d_mc<false>(sl, isk ? &maps.k : &maps.v, 0, kvrow + blk * 128, rank, bf);
          }
        }
      }
      if (elect_one()) mbar_expect_tx(bar_rx, UNIT);
      mbar_wait(bar_rel, 0);
      if (elect_one()) {
        bulk_load_stream(base + UNIT, g_act + (uint32_t)(rb * 80 + 16 + 63 - (cj & 1) * 32) * UNIT, UNIT, bar_rx);
      }
      if (b < NFFN) {
#pragma unroll 1
        for (int u = 0; u < 12; u++) {
          const uint32_t dst = base + unit_of(u < 4 ? FT_G : (u < 8 ? FT_U : FT_D), u & 3);
          if (elect_one()) mbar_expect_tx(bar_box + u * 8, UNIT);
          if (u == FB0 || u == FB1 || u == FB2) mbar_wait(bar_ring + (u == FB2 ? 16 : u == FB1 ? 8 : 0), 0);
          const int fp = u < FPB ? FPACE0 : FPACE;
          if (u >= fp) mbar_wait(bar_box + (u - fp) * 8, 0);
          if (elect_one()) {
            if (u < 8) tma2d(dst, u < 4 ? &maps.wg : &maps.wu, b * 32, (u & 3) * 256, bar_box + u * 8);
            else tma3d(dst, &maps.wd, 0, b * 32, (u - 8) * 4, bar_box + u * 8);
          }
        }
      }
    } else if (warp == 9) {
      const uint32_t target = 8 * (epoch + 1);
      uint32_t hmask = 0;
#pragma unroll 1
      for (int i = 0; i < 16; i++) {
        if (i == HDX) mbar_wait(bar_mod, 0);
        const int kt = (2 * cj + slice_of(i)) & 15;
        const uint32_t need = i == 15 ? 0xffffu : 1u << kt;
        if (i >= NRS && (hmask & need) != need) {
          uint32_t n = 0;
          do { hmask = __ballot_sync(0xffffffffu, ld_acquire(&g_cnt_h[rb * 32 + (lane & 15)]) == epoch + 1); watchdog(n); } while ((hmask & need) != need);
          PROF(1, lane == 0 && i == NRS, 26);
          fence_async();
        }
        mbar_wait(xempty + (i & 3) * 8, ((i >> 2) & 1) ^ 1);
        if (elect_one()) {
          mbar_expect_tx(xfull + (i & 3) * 8, UNIT);
          if (i < NRS) tma2d(base + (i & 3) * GST_BYTES, &maps.x, kt * 64, rb * 128, xfull + (i & 3) * 8);
          else bulk_load_stream(base + (i & 3) * GST_BYTES, g_act + (uint32_t)(rb * 80 + kt) * UNIT, UNIT, xfull + (i & 3) * 8);
        }
      }
      prefetch_map(&maps.wo);
#pragma unroll 1
      for (int t = 0; t < 4; t++) {
        if (t & 1) mbar_wait(bar_od, t >> 1);
#pragma unroll 1
        for (int p = 0; p < 32768 / OPS; p++) {
          const uint32_t w = p / (16384 / OPS), c = (p / (8192 / OPS)) & 1, off = w * 8192 + (p % (8192 / OPS)) * OPS;
          mbar_wait(bar_ofull + (t & 1) * 16 + w * 8, t >> 1);
          if (elect_one()) {
            bulk_store(g_act + (uint32_t)(rb * 80 + 16 + (cj * 4 + t) * 2 + c) * UNIT + off, base + unit_of(QT, 2 * t + c) + off, OPS);
            asm volatile("cp.async.bulk.commit_group;" ::: "memory");
            asm volatile("cp.async.bulk.wait_group.read %0;" ::"n"(OFL) : "memory");
          }
        }
        if (elect_one()) {
          asm volatile("cp.async.bulk.wait_group.read 0;" ::: "memory");
          mbar_arrive(t < 3 ? bar_ofree + t * 8 : bar_res);
          asm volatile("cp.async.bulk.wait_group 0;" ::: "memory");
          fence_async();
          red_release(&g_cnt_o[((rb * 4 + t) * 2 + (cj >> 2)) * 32], 2);
        }
        if (t) {
          wait_counter(&g_cnt_o[(rb * 8 + 2 * t + (cj & 1)) * 32], target);
          if (t & 1) wait_counter(&g_cnt_o[(rb * 8 + (t == 1 ? cj & 1 : 7 - (cj & 1))) * 32], target);
          if (elect_one()) mbar_arrive(t == 1 ? bar_ofree + 24 : bar_cnt + t * 8 - 16);
        }
      }
      PROF(2, lane == 0, 27);
      const uint32_t tag = epoch % 3 + 1;
      const uint32_t* inbox = g_cand + (lane & 15);
      mbar_wait(bar_ring + 16, 0);
      uint32_t c0 = ld_relaxed(inbox), n = 0;
#define CAND_STEP(cv)                                                                                        \
      {                                                                                                      \
        const bool valid = (cv & 3u) == tag, all = __all_sync(0xffffffffu, valid);                           \
        const uint32_t best = __reduce_max_sync(0xffffffffu, valid ? cv : 0u);                               \
        const uint32_t blk = __ffs(__ballot_sync(0xffffffffu, cv == best)) - 1;                              \
        if (best) sts2(par + PAR_CONST + 56, best, (blk << 7 | (~best >> 2 & 127)) | (all ? 0x1800 : 0x800)); \
        if (all) break;                                                                                      \
        cv = ld_relaxed(inbox);                                                                              \
      }
      while (true) { CAND_STEP(c0) watchdog(n); }
    } else {
      const int t2 = tid - 320;
      if (late && warp == 10) {
        mbar_wait(bar_hx + HWB * 8, 0);
        if (elect_one()) {
          tma2d(stage, &maps.wm, (b >> 1) * 32, rank * 512, bar_hw);
          tma2d(stage + 16384, &maps.wm, (b >> 1) * 32, rank * 512 + 256, bar_hw);
        }
      }
      mbar_wait(bar_hpub + (warp & 1) * 8, 0);
      PROF(1, t2 == 0, 24);
#pragma unroll 1
      for (int c = 0; c < 8; c++) {
        const uint32_t off = (warp & 1) * UNIT + c * 2048 + lane * 16;
        uint8_t* dst = g_act + (uint32_t)(rb * 80 + cj * 2) * UNIT + off;
        const uint4 v0 = lds4(stage + off), v1 = lds4(stage + off + 512), v2 = lds4(stage + off + 1024), v3 = lds4(stage + off + 1536);
        stg4(dst, v0); stg4(dst + 512, v1); stg4(dst + 1024, v2); stg4(dst + 1536, v3);
      }
      __syncwarp();
      PROF(1, t2 == 0, 15);
      if (lane == 0) {
        mbar_arrive(bar_pread);
        red_release(&g_cnt_h[rb * 32 + cj * 2 + (warp & 1)], 1);
        PROF(1, t2 == 0, 25);
        prefetch_map(&maps.wg); prefetch_map(&maps.wu); prefetch_map(&maps.wd); prefetch_map(&maps.out);
      }
      __syncwarp();
      if (b < NFFN) {
        mbar_wait(bar_go2, 0);
        const __nv_bfloat16* pg = ((b & 1) ? P.w_up : P.w_gate) + (b >> 1) * 64 + (size_t)t2 * FF;
        const __nv_bfloat16* pd = P.w_down + (size_t)b * 32768 + t2 * 64;
        PROF(2, t2 == 0, 13);
#pragma unroll 1
        for (int i = 0; i < WN; i += WB) {
          uint32_t v[WB];
#pragma unroll
          for (int u = 0; u < WB; u++) {
            const int k = i + u;
            asm volatile("ld.global.cg.L2::128B.u32 %0, [%1];" : "=r"(v[u]) : "l"(k < 16 ? pg + (size_t)k * 64 * FF : pd + (k - 16) * 4096));
          }
#pragma unroll
          for (int u = 1; u < WB; u++) v[0] ^= v[u];
          sts1(par + PAR_SINK + t2 * 4, v[0]);
        }
        PROF(2, t2 == 0, 14);
      }
      const uint32_t tag = epoch % 3 + 1;
      mbar_wait(bar_go, 0);
      bar_sync(4, 64);
      if (warp == 10) {
        const uint32_t* src = g_mod + 2 * DM + cj * 128 + lane * 4;
        const uint2 wr = *reinterpret_cast<const uint2*>(P.w_r + cj * 128 + lane * 4);
        uint4 vga, vsb, vcb, vgb;
        uint32_t n = 0;
        do {
          vga = ld_relaxed4(src); vsb = ld_relaxed4(src + DM); vcb = ld_relaxed4(src + 2 * DM); vgb = ld_relaxed4(src + 3 * DM);
          watchdog(n);
        } while (!__all_sync(0xffffffffu, tag_ok(vga, tag) && tag_ok(vsb, tag) && tag_ok(vcb, tag) && tag_ok(vgb, tag)));
        const float c0 = rbf(1.f + bf_hi(vcb.x)), c1 = rbf(1.f + bf_hi(vcb.y)), c2 = rbf(1.f + bf_hi(vcb.z)), c3 = rbf(1.f + bf_hi(vcb.w));
        const float a0 = c0 * bf_lo(wr.x), a1 = c1 * bf_hi(wr.x), a2 = c2 * bf_lo(wr.y), a3 = c3 * bf_hi(wr.y);
        const uint32_t h0 = pack_bf(a0, a1), h1 = pack_bf(a2, a3);
        const uint32_t t1 = par + PAR_T1 + (lane >> 2) * 64 + (lane & 1) * 32 + (lane & 2) * 2;
        sts1(t1, h0); sts1(t1 + 8, pack_bf(a0 - bf_lo(h0), a1 - bf_hi(h0)));
        sts1(t1 + 16, h1); sts1(t1 + 24, pack_bf(a2 - bf_lo(h1), a3 - bf_hi(h1)));
        const uint32_t tg = par + PAR_SINK + (lane >> 3) * 64 + (lane & 1) * 32 + (lane & 6) * 2;
        sts1(tg, __byte_perm(vga.x, vga.y, 0x7632)); sts1(tg + 16, __byte_perm(vga.z, vga.w, 0x7632));
        sts4(par + PAR_T2 + lane * 32, make_uint4(pack_bf(c0, c1), __byte_perm(vsb.x, vsb.y, 0x7632), __byte_perm(vgb.x, vgb.y, 0x7632), __byte_perm(vga.x, vga.y, 0x7632)));
        sts4(par + PAR_T2 + lane * 32 + 16, make_uint4(pack_bf(c2, c3), __byte_perm(vsb.z, vsb.w, 0x7632), __byte_perm(vgb.z, vgb.w, 0x7632), __byte_perm(vga.z, vga.w, 0x7632)));
      } else {
        const uint4 g = poll4((lane & 2) ? g_mod + 8 - (lane & 1) * 4 : g_mod + 5 * DM + b * 8 + (lane & 1) * 4, tag);
        sts1(par + PAR_CONST + 60, 0);
        if (lane < 2) sts4(par + PAR_CONST + 16 + lane * 16, g);
        else if (lane < 4) sts2(par + PAR_CONST + (lane - 2) * 8, __float_as_uint(untag_sum(g.x, g.y) + untag_sum(g.z, g.w)), epoch);
      }
      __syncwarp();
#pragma unroll 4
      for (int q = 0; q < 32; q++) st_b128(g_xch + ((size_t)b * 8 * 256 + q * 64 + t2) * 4, (epoch & 1) << 16, 0, 0, 0);
      for (int q = 0; q < 2; q++) st_relaxed4(g_stats + ((size_t)cj * SEQ + rb * 128 + q * 64 + t2) * 4, 0, 0, 0, 0);
      if (b < NFFN)
        for (int q = 0; q < 4; q++) st_relaxed4(g_ypart + ((size_t)(q * 32 + (t2 >> 1)) * NFFN + b) * 8 + (t2 & 1) * 4, 0, 0, 0, 0);
      st_relaxed4(g_row + rb * 2 * DM + (t2 >> 5) * DM + cj * 128 + (t2 & 31) * 4, 0, 0, 0, 0);
      __threadfence();
      mbar_arrive(bar_par);
      mbar_wait(bar_gate, 0);
      uint32_t have = 0, n = 0;
      while (true) {
        const uint32_t st = lds1(par + PAR_CONST + 60) >> 7;
        if ((st & 31) != have) {
          const uint32_t* hsrc = g_row + (st & 15) * 2 * DM + t2 * 4;
          uint4 hv[4];
          bool ok = true;
#pragma unroll
          for (int i = 0; i < 4; i++) hv[i] = ld_pairs(hsrc + i * 256);
#pragma unroll
          for (int i = 0; i < 4; i++) {
            sts2(base + ((FT_G >> i * 4) & 15) * UNIT + (warp & 1) * 8192 + 256 + lane * 8, hv[i].x, hv[i].z);
            ok = ok && hv[i].y == tag && hv[i].w == tag;
          }
          have = __all_sync(0xffffffffu, ok) ? st & 31 : 0;
        }
        if ((st ^ have) == 32) break;
        watchdog(n);
      }
      mbar_arrive(bar_sel);
    }
    __syncwarp();
    cluster_arrive();
    {
      const uint32_t tag = epoch % 3 + 1, t3 = tid - 256;
      mbar_wait(bar_win, 0);
      uint2 win = lds2(par + PAR_CONST + 56);
      win.y &= 0x7ff;
      const uint32_t* fsrc = g_row + (win.y >> 7) * 2 * DM + (b >> 1) * 16 + (t3 & 3) * 4 + (b & 1) * 2;
      const uint32_t* ysrc = g_ypart + (size_t)b * NFFN * 8 + min(t3, NFFN - 1) * 4;
      uint2 fh = ld_pair(fsrc), fx = ld_pair(fsrc + DM);
      if (PSL) __nanosleep(PSL);
      uint4 ya = ld_relaxed4(ysrc), yb = ld_relaxed4(ysrc + NFFN * 4);
      const float rwin = __uint_as_float(((int)win.x < 0 ? win.x & 0x7fffffffu : ~win.x) & ~0x1ffu);
      const float rs = rbf(rcp(1.f + __expf(-rbf(rwin))));
      uint32_t n = 0;
      while (__any_sync(0xffffffffu, fh.y != tag || fx.y != tag)) { fh = ld_pair(fsrc); fx = ld_pair(fsrc + DM); watchdog(n); }
      while (!__all_sync(0xffffffffu, tag_ok(ya, tag) && tag_ok(yb, tag))) {
        if (!tag_ok(ya, tag)) ya = ld_relaxed4(ysrc);
        if (!tag_ok(yb, tag)) yb = ld_relaxed4(ysrc + NFFN * 4);
        watchdog(n);
      }
      __syncwarp();
      PROF(8, t3 == 0, 5);
      float y0 = untag_sum(ya.x, yb.x), y1 = untag_sum(ya.y, yb.y), y2 = untag_sum(ya.z, yb.z), y3 = untag_sum(ya.w, yb.w);
      const bool u1 = lane & 2, u2 = lane & 4;
      y0 = (u1 ? y2 : y0) + __shfl_xor_sync(0xffffffffu, u1 ? y0 : y2, 2);
      y1 = (u1 ? y3 : y1) + __shfl_xor_sync(0xffffffffu, u1 ? y1 : y3, 2);
      y0 = (u2 ? y1 : y0) + __shfl_xor_sync(0xffffffffu, u2 ? y0 : y1, 4);
      y0 += __shfl_xor_sync(0xffffffffu, y0, 8);
      if (!(lane & 8)) sts1(par + PAR_RED + 64 + (t3 >> 4) * 32 + ((lane & 1) * 4 + (lane & 2) + ((lane >> 2) & 1)) * 4, __float_as_uint(y0));
      bar_sync(4, 128);
      if (t3 < 4) {
        y0 = 0.f; y1 = 0.f;
#pragma unroll
        for (int w4 = 0; w4 < 7; w4++) {
          const uint2 v = lds2(par + PAR_RED + 64 + w4 * 32 + t3 * 8);
          y0 += __uint_as_float(v.x); y1 += __uint_as_float(v.y);
        }
        const uint2 gv = lds2(par + PAR_CONST + 16 + t3 * 8);
        const uint32_t upd = hmul2(pack_bf(y0, y1), pack_bf(rs, rs));
        *reinterpret_cast<uint32_t*>(P.out + (size_t)win.y * DM + b * 8 + t3 * 2) =
            hadd2(fx.x, hmul2(__byte_perm(gv.x, gv.y, 0x7632), hadd2(fh.x, upd)));
        if (b == 0 && t3 == 0) st_relaxed(&g_epoch, epoch + 1);
      }
      PROF(31, t3 == 0, 36);
    }
    cluster_wait();
  } else {
    const int wg = warp >> 2;

    uint32_t tag;
    {
      uint32_t* const pmod = g_modp + rank * 2 * DM + (b >> 1) * 32 + lane;
      uint32_t* const pln = g_ln1 + (rb * 128 + cj * 16 + warp) * 4;
      const uint32_t cv = ldg_nc1(P.c + rank * 512 + tid * 2);
      const uint32_t epoch = ld_relaxed(&g_epoch);
      if (warp == 0) st_relaxed(pmod, 0);
      if (lane == 0) { st_b128(pln, 0, 0, 0, 0); st_b128(pln + 32, 0, 0, 0, 0); }
      asm volatile("setmaxnreg.inc.sync.aligned.u32 232;");
      sts1(par + tid * 4, pack_bf(silu_f(bf_lo(cv)), silu_f(bf_hi(cv))));
      bar_sync(1, 320);
      tag = epoch % 3 + 1;
#pragma unroll
      for (int part = 0; part < 4; part++) {
        if (!(part & 1)) {
          const uint32_t xa = base + (2 + part / 2) * GST_BYTES + warp * 2048 + lane * 16;
          mbar_wait(bar_hx + part * 4, 0);
          float s0 = 0.f, s1 = 0.f, q0 = 0.f, q1 = 0.f;
#pragma unroll
          for (int q = 0; q < 4; q++) {
            const uint4 xv = lds4(xa + q * 512);
            const uint32_t u[4] = {xv.x, xv.y, xv.z, xv.w};
#pragma unroll
            for (int e = 0; e < 4; e++) { const float lo = bf_lo(u[e]), hi = bf_hi(u[e]); s0 += lo; s1 += hi; q0 += lo * lo; q1 += hi * hi; }
          }
          s0 += s1; q0 += q1;
#pragma unroll
          for (int o = 16; o > 0; o >>= 1) { s0 += __shfl_xor_sync(0xffffffffu, s0, o); q0 += __shfl_xor_sync(0xffffffffu, q0, o); }
          const float mean = s0 * (1.f / DM);
          float mb, sd;
          ln_scalars(mean, fmaxf(q0 * (1.f / DM) - mean * mean, 0.f), mb, sd);
          uint32_t ih, il;
          split_inv(sd, ih, il);
          if (lane == 0) st_b128(pln + part * 16, pack_bf(mb, mb), ih, il, tag);
          PROF(1, tid == 0 && part == 2, 4);
        } else if (late == (part == 3)) {
          const uint32_t fr = (lane & 7) + (lane >> 4) * 8, tq = lane & 3;
          const uint32_t wa = stage + warp * 4096 + fr * 64 + ((((lane >> 3) & 1) ^ ((fr >> 1) & 3)) << 4);
          uint32_t sc[8];
#pragma unroll
          for (int k = 0; k < 8; k++) sc[k] = lds1(par + warp * 128 + k * 16 + tq * 4);
          float d0[4] = {0.f, 0.f, 0.f, 0.f}, d1[4] = {0.f, 0.f, 0.f, 0.f};
          mbar_wait(bar_hw, 0);
#pragma unroll
          for (int ks = 0; ks < 4; ks++) {
            uint32_t w[8];
            ldmatrix4t(wa + ks * 1024, w[0], w[1], w[2], w[3]);
            ldmatrix4t((wa ^ 32) + ks * 1024, w[4], w[5], w[6], w[7]);
            mma16816(d0, w[0], w[1], w[2], w[3], sc[2 * ks], sc[2 * ks + 1]);
            mma16816(d1, w[4], w[5], w[6], w[7], sc[2 * ks], sc[2 * ks + 1]);
          }
          sts1(base + 2 * GST_BYTES + warp * 2048 + (tq * 8 + (lane >> 2)) * 4, __float_as_uint((tq & 2) ? ((tq & 1) ? d1[2] : d1[0]) : ((tq & 1) ? d0[2] : d0[0])));
          bar_sync(1, 256);
          if (warp == 0) {
            float s = 0.f;
#pragma unroll
            for (int w8 = 0; w8 < 8; w8++) s += __uint_as_float(lds1(base + 2 * GST_BYTES + w8 * 2048 + lane * 4));
            st_relaxed(pmod, (__float_as_uint(s) & ~3u) | tag);
          }
          PROF(1, tid == 0, 3);
        }
      }
      cluster_wait();
      if (wg == 1) bar_arrive(2, 256);
    }

    float f0 = 0.f, f1 = 0.f;
    const uint32_t rempty = lane < 2 ? mapa(bempty, lane & 1) : 0;
    constexpr uint32_t GE = NSLOT * 8 + 32;
    float o[64], s[64];
#pragma unroll 1
    for (int ps = 0; ps < 3; ps++) {
      {
        const uint32_t xt = ps == 1 ? XT1 : XT2, wt = ps == 1 ? WT1 : WT2;
        const int nst = ps == 2 ? 28 : 14;
        if (ps == 0) {
          float ga[64], gb[64];
#pragma unroll
          for (int i = 0; i < 64; i++) { ga[i] = 0.f; gb[i] = 0.f; }
          uint32_t a[2][16];
          const uint32_t l = fresh_lane();
          uint32_t fa[4];
#pragma unroll
          for (int kk = 0; kk < 4; kk++) fa[kk] = (base + wg * 8192 + frag_offset(warp)) ^ (kk * 32);
          const uint32_t mt = par + (l & 3) * 16;
          auto fetch = [&](int i, uint32_t (&f)[16], uint32_t z) {
            mbar_wait(xfull + (i & 3) * 8, i >> 2);
#pragma unroll
            for (int kk = 0; kk < 4; kk++) ldmatrix4(fa[kk] + (i & 3) * GST_BYTES + z, f[4 * kk], f[4 * kk + 1], f[4 * kk + 2], f[4 * kk + 3]);
          };
          const bool oddw = HALFW && (warp & 2);
          auto table_slot = [&]() { const uint32_t k = fresh_lane(); return HALFW ? (warp & 1) * 64 + (k >> 4) * 32 + (warp & 2) * 8 + (k & 15) : (warp & 3) * 32 + k; };
          auto write_table = [&](uint32_t t7, const uint4& m0, const uint4& m1) {
            float c0 = untag_sum(m0.x, m1.x), c1 = untag_sum(m0.y, m1.y), c2 = untag_sum(m0.z, m1.z), c3 = untag_sum(m0.w, m1.w);
            if (wg) { c0 = 1.f + rbf(c0); c1 = 1.f + rbf(c1); c2 = 1.f + rbf(c2); c3 = 1.f + rbf(c3); }
            const uint32_t d = par + (t7 >> 2) * 64 + (t7 & 1) * 32 + (t7 & 2) * 2 + (wg ? 0 : 8);
            sts1(d, pack_bf(c0, c1));
            sts1(d + 16, pack_bf(c2, c3));
          };
          uint4 r0, r1;
          {
            const uint32_t t7 = table_slot();
            const uint32_t* pm = g_modp + wg * DM + ((cj * 128 + t7 * 4) & (DM - 1));
            const uint32_t* pr = g_ln1 + (rb * 128 + warp * 16 + (l >> 2)) * 4;
            uint4 m0 = make_uint4(tag, tag, tag, tag), m1 = m0;
            if (!oddw) { m0 = ld_relaxed4(pm); m1 = ld_relaxed4(pm + 2 * DM); }
            r0 = ld_b128(pr); r1 = ld_b128(pr + 32);
            fetch(0, a[0], 0); fetch(1, a[1], 0);
            uint32_t n = 0;
            bool written = false;
#pragma unroll 1
            while (true) {
              uint32_t miss;
              asm volatile("{ .reg .pred p0, p1, p2, p3; .reg .b32 t, u;\n"
                           "lop3.b32 t, %1, %2, %19, 0x7e; lop3.b32 u, %3, %4, %19, 0x7e; or.b32 t, t, u; and.b32 t, t, 3; setp.ne.u32 p0, t, 0;\n"
                           "lop3.b32 t, %5, %6, %19, 0x7e; lop3.b32 u, %7, %8, %19, 0x7e; or.b32 t, t, u; and.b32 t, t, 3; setp.ne.u32 p1, t, 0;\n"
                           "setp.ne.u32 p2, %12, %19; setp.ne.u32 p3, %16, %19;\n"
                           "@p0 ld.relaxed.gpu.global.v4.u32 {%1, %2, %3, %4}, [%17];\n"
                           "@p1 ld.relaxed.gpu.global.v4.u32 {%5, %6, %7, %8}, [%17 + 8192];\n"
                           "@p2 ld.relaxed.gpu.global.v4.u32 {%9, %10, %11, %12}, [%18];\n"
                           "@p3 ld.relaxed.gpu.global.v4.u32 {%13, %14, %15, %16}, [%18 + 128];\n"
                           "or.pred p0, p0, p1; or.pred p2, p2, p3; vote.sync.any.pred p0, p0, 0xffffffff; vote.sync.any.pred p2, p2, 0xffffffff;\n"
                           "selp.u32 t, 1, 0, p0; selp.u32 u, 2, 0, p2; or.b32 %0, t, u; }"
                           : "=r"(miss), "+r"(m0.x), "+r"(m0.y), "+r"(m0.z), "+r"(m0.w), "+r"(m1.x), "+r"(m1.y), "+r"(m1.z), "+r"(m1.w),
                             "+r"(r0.x), "+r"(r0.y), "+r"(r0.z), "+r"(r0.w), "+r"(r1.x), "+r"(r1.y), "+r"(r1.z), "+r"(r1.w)
                           : "l"(pm), "l"(pr), "r"(tag) : "memory");
              if (!(miss & 1) && !written) {
                written = true;
                write_table(t7, m0, m1);
                mbar_arrive(bar_mod);
              }
              if (!miss) break;
              watchdog(n);
            }
          }
          const uint32_t zero = r0.w ^ tag;
          auto normalize = [&](uint32_t (&f)[16]) {
#pragma unroll
            for (int k = 0; k < 16; k += 2) { f[k] = ln_norm(f[k], r0.x, r0.y, r0.z); f[k + 1] = ln_norm(f[k + 1], r1.x, r1.y, r1.z); }
          };
          auto modulate = [&](int i, uint32_t (&f)[16]) {
#pragma unroll
            for (int kk = 0; kk < 4; kk++) {
              const uint4 m = lds4(mt + slice_of(i) * 256 + kk * 64);
              f[4 * kk] = MODUL(f[4 * kk], m.x, m.z); f[4 * kk + 1] = MODUL(f[4 * kk + 1], m.x, m.z);
              f[4 * kk + 2] = MODUL(f[4 * kk + 2], m.y, m.w); f[4 * kk + 3] = MODUL(f[4 * kk + 3], m.y, m.w);
            }
            keep(f);
            mbar_arrive_pred(xempty + (i & 3) * 8, l == 0);
          };
          auto publish = [&](int u, uint32_t (&f)[16]) {
#pragma unroll
            for (int kk = 0; kk < 4; kk++) stmatrix4(fa[kk] + OFF_STAGE + u * UNIT, f[4 * kk], f[4 * kk + 1], f[4 * kk + 2], f[4 * kk + 3]);
            __syncwarp();
            mbar_arrive_pred(bar_hpub + u * 8, l == 0);
          };
          auto multiply = [&](int i, uint32_t (&f)[16]) {
            mbar_wait(gfull + (i & 3) * 8, i >> 2);
            const uint64_t db = make_desc(base + (i & 3) * GST_BYTES + UNIT, 8192, 1024);
            wg_fence();
#pragma unroll
            for (int kk = 0; kk < 4; kk++) mma256_rs(ga, gb, f[4 * kk], f[4 * kk + 1], f[4 * kk + 2], f[4 * kk + 3], db + kk * 128);
            wg_commit();
          };
          auto next = [&](int i, uint32_t (&f)[16]) {
            wg_wait<1>();
            mbar_arrive_cl(rempty, GE + ((i + 2) & 3) * 8);
            uint32_t z = zero;
#pragma unroll
            for (int k = 0; k < 16; k += 2) asm volatile("lop3.b32 %0, %1, %2, %0, 0xA8;" : "+r"(z) : "r"(f[k]), "r"(f[k + 1]));
            fetch(i, f, z);
            normalize(f); modulate(i, f); multiply(i, f);
          };
          normalize(a[0]); normalize(a[1]);
          keep(a[0]); keep(a[1]);
          mbar_wait(bar_mod, 0);
          PROF(1, tid == 0, 2);
          modulate(0, a[0]); multiply(0, a[0]); publish(0, a[0]);
          modulate(1, a[1]); multiply(1, a[1]);
          if (oddw) {
            const uint32_t t7 = table_slot();
            const uint32_t* pm = g_modp + wg * DM + ((cj * 128 + t7 * 4) & (DM - 1));
            uint4 m0, m1;
            uint32_t n = 0;
            do { m0 = ld_relaxed4(pm); m1 = ld_relaxed4(pm + 2 * DM); watchdog(n); } while (!__all_sync(0xffffffffu, tag_ok(m0, tag) && tag_ok(m1, tag)));
            write_table(t7, m0, m1);
            mbar_arrive(bar_mod2);
          }
          if (HALFW) mbar_wait(bar_mod2, 0); else publish(1, a[1]);
#pragma unroll 1
          for (int i = 2; i < NRS; i += 2) {
            next(i, a[0]);
            if (HALFW && i == 2) publish(1, a[0]);
            next(i + 1, a[1]);
          }
          wg_wait<1>();
          mbar_arrive_cl(rempty, GE + ((NRS + 2) & 3) * 8);
#pragma unroll 1
          for (int i = NRS; i < 14; i++) {
            mbar_wait(xfull + (i & 3) * 8, (i >> 2) & 1);
            mbar_wait(gfull + (i & 3) * 8, (i >> 2) & 1);
            const uint32_t xa = base + (i & 3) * GST_BYTES;
            const uint64_t da = make_desc(xa + wg * 8192, 16, 1024), db = make_desc(xa + UNIT, 8192, 1024);
            if (i == 13) bar_sync(2 + wg, 256);
            wg_fence();
#pragma unroll
            for (int kk = 0; kk < 4; kk++) mma256_ss(ga, gb, da + kk * 2, db + kk * 128, 1);
            wg_commit();
            if (i == 13) bar_arrive(3 - wg, 256);
            wg_wait<1>();
            uint32_t z = zero;
#pragma unroll
            for (int k = 0; k < 16; k += 2) asm volatile("lop3.b32 %0, %1, %2, %0, 0xA8;" : "+r"(z) : "r"(a[1][k]), "r"(a[1][k + 1]));
            mbar_arrive_cl(rempty, GE + ((i + 3) & 3) * 8 + z);
            mbar_arrive_pred(xempty + ((i + 3) & 3) * 8, l == 0 && i != NRS);
          }
          mbar_wait(xfull + 16, 1);
          wg_wait<0>();
          keep(ga); keep(gb);
#pragma unroll
          for (int i = 0; i < 64; i++) {
            asm volatile("mov.b32 %0, %1;" : "=f"(s[i]) : "f"(ga[i]));
            asm volatile("mov.b32 %0, %1;" : "=f"(o[i]) : "f"(gb[i]));
          }
        } else {
          float ga[64], gb[64];
#pragma unroll
          for (int i = 0; i < 64; i++) {
            asm volatile("mov.b32 %0, %1;" : "=f"(ga[i]) : "f"(s[i]));
            asm volatile("mov.b32 %0, %1;" : "=f"(gb[i]) : "f"(o[i]));
          }
#pragma unroll 1
          for (int i = 0; i < nst; i++) {
            mbar_wait(gfull + (i & 3) * 8, (i >> 2) & 1);
            const uint64_t da = make_desc(base + unit_of(xt, i & 3) + wg * 8192, 16, 1024), db = make_desc(base + unit_of(wt, i & 3), 8192, 1024);
            if (i == nst - 1) bar_sync(2 + wg, 256);
            wg_fence();
#pragma unroll
            for (int kk = 0; kk < 4; kk++) mma256_ss(ga, gb, da + kk * 2, db + kk * 128, kk ? 1 : i);
            wg_commit();
            if (i == nst - 1) bar_arrive(3 - wg, 256);
            wg_wait<1>();
            mbar_arrive_cl(rempty, GE + ((i + 3) & 3) * 8, i != 0);
            PROF(4, tid == 0 && (i & 3) == 0, 40 + (ps - 1) * 4 + i / 4);
          }
          wg_wait<0>();
          keep(ga); keep(gb);
#pragma unroll
          for (int i = 0; i < 64; i++) {
            asm volatile("mov.b32 %0, %1;" : "=f"(s[i]) : "f"(ga[i]));
            asm volatile("mov.b32 %0, %1;" : "=f"(o[i]) : "f"(gb[i]));
          }
        }
        mbar_arrive_cl(rempty, GE + (ps == 2 ? 24 : 8));
        if (ps == 2) break;
      }
      const uint32_t qw = base + wg * 8192, qt = QT >> (16 * ps), at = ps ? AT1 : AT0;
      {
        const uint32_t wt = ps ? WT1 : WT0;
        const uint64_t da0 = make_desc(qw + unit_of(qt, 2), 16, 1024), da1 = make_desc(qw + unit_of(qt, 3), 16, 1024);
        const uint64_t db0 = make_desc(base + unit_of(wt, 2), 8192, 1024), db1 = make_desc(base + unit_of(wt, 3), 8192, 1024);
        mbar_wait(gfull + 16, 1);
        bar_sync(2 + wg, 256);
        wg_fence();
#pragma unroll
        for (int kk = 0; kk < 4; kk++) mma_ss<1>(s, da0 + kk * 2, db0 + kk * 128, 1);
        wg_commit();
        mbar_wait(xfull + 24, 1);
        mbar_wait(gfull + 24, 1);
        wg_fence();
#pragma unroll
        for (int kk = 0; kk < 4; kk++) mma_ss<1>(s, da1 + kk * 2, db1 + kk * 128, 1);
        wg_commit();
        bar_arrive(3 - wg, 256);
        mbar_wait(ps == 0 ? bar_pread : bar_ofree + 8, 0);
        wg_wait<0>();
        keep(s);
        PROF(2, tid == 0, 8 + ps * 8);
        uint32_t q[32];
        pack_p(s, q);
#pragma unroll
        for (int i = 0; i < 4; i++) stmatrix4((qw + unit_of(qt, 0) + frag_offset(warp)) ^ (i << 5), q[4 * i], q[4 * i + 1], q[4 * i + 2], q[4 * i + 3]);
        keep(q);
        bar_sync(2 + wg, 256);
        wg_fence();
#pragma unroll
        for (int kk = 0; kk < 8; kk++) mma_ss<1>(o, (kk < 4 ? da0 : da1) + (kk & 3) * 2, (kk < 4 ? db0 : db1) + UNIT / 16 + (kk & 3) * 128, 1);
        wg_commit();
        mbar_wait(bfull, 0);
        wg_fence();
        const uint64_t dk = make_desc(base + unit_of(at, 0), 16, 1024);
#pragma unroll
        for (int kk = 0; kk < 8; kk++) mma_rs<0>(s, q[4 * kk], q[4 * kk + 1], q[4 * kk + 2], q[4 * kk + 3], dk + (kk >> 2) * 1024 + (kk & 3) * 2, kk != 0);
        wg_commit();
        bar_arrive(3 - wg, 256);
#pragma unroll
        for (int i = 4; i < 8; i++) stmatrix4((qw + unit_of(qt, 1) + frag_offset(warp)) ^ ((i & 3) << 5), q[4 * i], q[4 * i + 1], q[4 * i + 2], q[4 * i + 3]);
        wg_wait<1>();
        keep(o);
        mbar_arrive_cl(rempty, GE + 16);
        mbar_arrive_cl(rempty, GE + 24);
        store_chunk<0>(o, qw + unit_of(qt, 2) + frag_offset(warp));
        store_chunk<1>(o, qw + unit_of(qt, 3) + frag_offset(warp));
        wg_wait<0>();
        keep(s);
        mbar_arrive_cl(rempty, 0);
      }
      PROF(4, tid == 0 && ps == 1, 61);
      float l0 = 0.f, l1 = 0.f;
      auto step = [&](auto odd_c, const int j, uint32_t (&pw)[32], uint32_t (&pr)[32]) {
        constexpr bool ODD = decltype(odd_c)::value;
        const bool first = !ODD && (j & 2) == 0, last = ODD && j == 7;
        const uint32_t ph = (j >> 1) & 1;
        float i0, i1, a0, a1;
        const bool so = !ODD && j == 4;
        if (so) { i0 = inv_quad_sum(l0); i1 = inv_quad_sum(l1); l0 = 0.f; l1 = 0.f; }
        bool redo = !ODD && (j | ps) == 0;
        while (true) {
          if (redo) {
            float m0 = fmaxf(s[0], s[1]), m1 = fmaxf(s[2], s[3]);
#pragma unroll
            for (int i = 1; i < 16; i++) { m0 = fmaxf(m0, fmaxf(s[4 * i], s[4 * i + 1])); m1 = fmaxf(m1, fmaxf(s[4 * i + 2], s[4 * i + 3])); }
            m0 = fmaxf(m0, __shfl_xor_sync(0xffffffffu, m0, 1)); m1 = fmaxf(m1, __shfl_xor_sync(0xffffffffu, m1, 1));
            m0 = fmaxf(m0, __shfl_xor_sync(0xffffffffu, m0, 2)); m1 = fmaxf(m1, __shfl_xor_sync(0xffffffffu, m1, 2));
            m0 *= SCL2; m1 *= SCL2;
            if (!first) {
              m0 = fmaxf(m0, f0); m1 = fmaxf(m1, f1);
              const float c0 = ex2(f0 - m0), c1 = ex2(f1 - m1);
              l0 *= c0; l1 *= c1;
              wg_wait<0>();
              keep(o);
#pragma unroll
              for (int i = 0; i < 16; i++) { o[4 * i] *= c0; o[4 * i + 1] *= c0; o[4 * i + 2] *= c1; o[4 * i + 3] *= c1; }
            }
            f0 = m0; f1 = m1;
          }
          float b0 = 0.f, b1 = 0.f;
          a0 = 0.f; a1 = 0.f;
#pragma unroll
          for (int i = 0; i < 16; i++) {
            const float e0 = ex2(fmaf(s[4 * i], SCL2, -f0)), e1 = ex2(fmaf(s[4 * i + 1], SCL2, -f0));
            const float e2 = ex2(fmaf(s[4 * i + 2], SCL2, -f1)), e3 = ex2(fmaf(s[4 * i + 3], SCL2, -f1));
            a0 += e0; b0 += e1; a1 += e2; b1 += e3;
            pw[2 * i] = pack_bf(e0, e1); pw[2 * i + 1] = pack_bf(e2, e3);
            if (i == VREL) {
#pragma unroll
              for (int k = 0; k < 2 * VREL + 2; k++) asm volatile("" : "+r"(pw[k])::"memory");
              mbar_wait(bar_mod, 0);
              wg_wait<0>();
              mbar_arrive_cl(rempty, ODD ? 16 : 0, !redo && (ODD || j));
#pragma unroll
              for (int k = 4 * VREL + 4; k < 64; k++) asm volatile("" : "+f"(s[k])::"memory");
            }
          }
          a0 += b0; a1 += b1;
          if (redo) break;
          redo = __any_sync(0xffffffffu, !(a0 + a1 < 0x1p90f));
          if (first) {
            uint32_t m0 = __ballot_sync(0xffffffffu, a0 > 0x1p-80f), m1 = __ballot_sync(0xffffffffu, a1 > 0x1p-80f);
            m0 |= m0 >> 1; m1 |= m1 >> 1; m0 |= m0 >> 2; m1 |= m1 >> 2;
            redo = redo || (m0 & m1 & 0x11111111u) != 0x11111111u;
          }
          if (!redo) break;
        }
        l0 += a0; l1 += a1;
        keep(pw);
        keep(o);
        if (so) store_chunk<0>(o, i0, i1, qw + unit_of(qt, 0) + frag_offset(warp));
        keep(o);
        if (j == (ODD ? 5 : 0)) { fence_async_smem(); if (ODD) mbar_arrive(bar_ofull + wg * 8); }
        mbar_wait(bfull + (ODD ? 24 : 8), ph);
        bar_sync(2 + wg, 256);
        if (!last) {
          const uint32_t qn = qt >> (j >= 3 ? 8 : 0);
          wg_fence();
          issue_qk(s, qw + unit_of(qn, 0), qw + unit_of(qn, 1), base + unit_of(at, ODD ? 3 : 1));
          wg_commit();
          mbar_wait(bfull + (ODD ? 0 : 16), ODD ? ph ^ 1 : ph);
        }
        if (so) { store_chunk<1>(o, i0, i1, qw + unit_of(qt, 1) + frag_offset(warp)); keep(o); }
        wg_fence();
        issue_pv(o, pw, base + unit_of(at, ODD ? (last ? 3 : 0) : 2), !first);
        wg_commit();
        bar_arrive(3 - wg, 256);
        wg_wait<1>();
        keep(s);
        mbar_arrive_cl(rempty, ODD ? 24 : 8, !last);
        PROF(4, tid == 0 && ps == 1, 51 + j);
      };
      uint32_t pa[32], pb[32];
#pragma unroll 1
      for (int j = 0; j < 8; j += 2) {
        step(std::false_type{}, j, pa, pb);
        step(std::true_type{}, j + 1, pb, pa);
      }
      {
        const float i0 = inv_quad_sum(l0), i1 = inv_quad_sum(l1);
        wg_wait<0>();
        keep(o);
        mbar_arrive_cl(rempty, 24);
        store_chunk<0>(o, i0, i1, qw + unit_of(qt, 2) + frag_offset(warp));
        store_chunk<1>(o, i0, i1, qw + unit_of(qt, 3) + frag_offset(warp));
        fence_async_smem();
        mbar_arrive(bar_ofull + 16 + wg * 8);
      }
      PROF(2, tid == 0, 10 + ps * 8);
    }

    const int ln = fresh_lane(), g = ln >> 2, tq = ln & 3, ct = warp * 32 + ln;
    const bool lane0 = ln == 0;
    const int lrow0 = warp * 16 + g;
    const int grow0 = rb * 128 + lrow0;
    const uint32_t res = base + OFF_RES, trow = res + wg * 8192 + frag_offset(warp);
    uint32_t xr[32];
    uint4 sv[4], own;
    uint32_t* sp[4];
#pragma unroll
    for (int k = 0; k < 4; k++) sp[k] = g_stats + ((((tq >> 1) * 4 + k) ^ cj) * SEQ + grow0 + (tq & 1) * 8) * 4;
    {
      const uint64_t da = make_desc(base + wg * 8192, 16, 1024), db = make_desc(base, 8192, 1024);
      constexpr int U = UNIT / 16;
#define HALF_STAGE(acc, xu, wu) _Pragma("unroll") for (int kk = 0; kk < 4; kk++) mma_ss<1>(acc, da + (xu) * U + kk * 2, db + (wu) * U + kk * 128, 1)
      PROF(10, ct == PT, 19); STAMP(0);
      cluster_arrive();
      mbar_wait(gfull, 1);
      mbar_wait(gfull + 8, 1);
      bar_sync(2 + wg, 256);
      wg_fence();
      HALF_STAGE(o, 7, 1);
      HALF_STAGE(o, 8, 3);
      wg_commit();
      STAMP(16);
      mbar_wait(gfull + 16, 1);
      STAMP(17);
      wg_fence();
      HALF_STAGE(o, 6, 11);
      wg_commit();
      bar_arrive(3 - wg, 256);
      mbar_wait(bar_par, 0);
      uint32_t* xo = g_xch + ((size_t)b * 8 * 256 + ct) * 4;
      const uint32_t* xi = g_xch + ((size_t)(b ^ 2) * 8 * 256 + ct) * 4;
      const uint32_t par1 = (~lds1(par + PAR_CONST + 4) & 1) << 16;
      wg_wait<1>();
      mbar_arrive_pred(bar_rel, lane0);
      wg_wait<0>();
      keep(o);
      mbar_arrive_pred(bar_ring, lane0);
      PROF(8, ct == PT, 20); STAMP(1);
#define SEND(i) st_b128(xo + (i) * 1024, (pack_bf(o[8 * (i)], o[8 * (i) + 1]) & ~0x10000u) | par1, pack_bf(o[8 * (i) + 2], o[8 * (i) + 3]), \
                        pack_bf(o[8 * (i) + 4], o[8 * (i) + 5]), pack_bf(o[8 * (i) + 6], o[8 * (i) + 7]))
#pragma unroll
      for (int i = 0; i < NS1; i++) SEND(i);
      PROF(8, ct == PT, 21); STAMP(2);
      bar_sync(2 + wg, 256);
      wg_fence();
      HALF_STAGE(s, 7, 0);
      HALF_STAGE(s, 8, 2);
      HALF_STAGE(s, 6, 10);
      wg_commit();
      bar_arrive(3 - wg, 256);
      STAMP(18);
      mbar_wait(gfull + 24, 1);
#pragma unroll
      for (int i = NS1; i < 8; i++) SEND(i);
      uint4 v[8];
#pragma unroll
      for (int i = 0; i < LD1; i++) v[i] = ld_b128(xi + i * 1024);
      STAMP(19);
      mbar_wait(bar_xres, 0);
      wg_wait<0>();
      mbar_arrive_pred(bar_ring + 8, lane0);
      bar_sync(2 + wg, 256);
      STAMP(20);
#pragma unroll
      for (int i = LD1; i < LD2; i++) v[i] = ld_b128(xi + i * 1024);
      mbar_wait(bar_xres, 0);
      wg_fence();
      HALF_STAGE(s, 9, 4);
      wg_commit();
      mbar_wait(bar_rx, 0);
      wg_fence();
      HALF_STAGE(s, 1, 5);
      wg_commit();
      bar_arrive(3 - wg, 256);
      STAMP(21);
#pragma unroll
      for (int i = LD2; i < 8; i++) v[i] = ld_b128(xi + i * 1024);
      if (LD2 < 8) mbar_wait(bar_xres, 0);
      wg_wait<0>();
      keep(s);
      mbar_arrive_pred(bar_ring + 16, lane0);
      PROF(10, ct == PT, 23); STAMP(4);
#pragma unroll
      for (int i = 0; i < 16; i += 2) ldmatrix4((trow ^ ((i & 7) << 4)) + (i >> 3) * 16384, xr[2 * i], xr[2 * i + 1], xr[2 * i + 2], xr[2 * i + 3]);
      uint32_t ga[16];
      uint4 bw[8];
#pragma unroll
      for (int i = 0; i < 8; i++) {
        if (!(i & 1)) {
          const uint4 t = lds4(par + PAR_SINK + i * 32 + tq * 16);
          ga[2 * i] = t.x; ga[2 * i + 1] = t.y; ga[2 * i + 2] = t.z; ga[2 * i + 3] = t.w;
        }
        bw[i] = lds4(par + PAR_T1 + i * 64 + tq * 16);
        if (!(g & 1)) { bw[i].x = 0x3f803f80u; bw[i].y = 0x3f803f80u; }
      }
      uint32_t pk[32];
      pack_p(s, pk);
      keep(pk);
      {
        uint32_t n = 0, miss;
        do {
          miss = 0;
#pragma unroll
          for (int i = 0; i < 8; i++) miss |= v[i].x ^ par1;
          miss = __any_sync(0xffffffffu, miss & 0x10000u);
          if (miss) {
#pragma unroll
            for (int i = 0; i < 8; i++)
              asm volatile("{ .reg .pred p; .reg .b32 t; xor.b32 t, %0, %5; and.b32 t, t, 0x10000; setp.ne.u32 p, t, 0;\n"
                           "@p ld.relaxed.gpu.global.v4.u32 {%0, %1, %2, %3}, [%4]; }"
                           : "+r"(v[i].x), "+r"(v[i].y), "+r"(v[i].z), "+r"(v[i].w) : "l"(xi + i * 1024), "r"(par1) : "memory");
          }
          watchdog(n);
        } while (miss);
      }
      PROF(8, ct == PT, 22); STAMP(3);
      float ds[4] = {0.f, 0.f, 0.f, 0.f}, dl[4] = {0.f, 0.f, 0.f, 0.f}, q0[4] = {0.f, 0.f, 0.f, 0.f}, q1[4] = {0.f, 0.f, 0.f, 0.f};
#pragma unroll
      for (int i = 0; i < 8; i++) {
        const uint32_t u0 = hfma2(ga[2 * i], hadd2(pk[4 * i], v[i].x & ~0x10000u), xr[4 * i]);
        const uint32_t u1 = hfma2(ga[2 * i], hadd2(pk[4 * i + 1], v[i].y), xr[4 * i + 1]);
        const uint32_t u2 = hfma2(ga[2 * i + 1], hadd2(pk[4 * i + 2], v[i].z), xr[4 * i + 2]);
        const uint32_t u3 = hfma2(ga[2 * i + 1], hadd2(pk[4 * i + 3], v[i].w), xr[4 * i + 3]);
        xr[4 * i] = u0; xr[4 * i + 1] = u1; xr[4 * i + 2] = u2; xr[4 * i + 3] = u3;
        mma16816(ds, u0, u1, u2, u3, bw[i].x, bw[i].y);
        mma16816(dl, u0, u1, u2, u3, bw[i].z, bw[i].w);
        mma16816(q0, u0, u1, u2, u3, u0, u2);
        mma16816(q1, u0, u1, u2, u3, u1, u3);
      }
      const float sqa = __shfl_sync(0xffffffffu, (g & 1) ? q0[1] : q0[0], g * 4 + (g >> 1));
      const float sqb = __shfl_sync(0xffffffffu, (g & 1) ? q1[3] : q1[2], g * 4 + (g >> 1));
      own = (tq & 1) ? make_uint4(__float_as_uint(ds[2]), __float_as_uint(sqb), __float_as_uint(ds[3] + dl[3]), tag)
                                 : make_uint4(__float_as_uint(ds[0]), __float_as_uint(sqa), __float_as_uint(ds[1] + dl[1]), tag);
      if (tq < 2) st_b128(sp[0], own.x, own.y, own.z, own.w);
#pragma unroll
      for (int k = 0; k < 4; k++) sv[k] = make_uint4(0, 0, 0, 0);
    }
    PROF(8, ct == PT, 29); STAMP(5);
    uint32_t mm, ih, il;
    float rbest;
    uint32_t wf[128];
    const uint32_t frow = (ln & 7) + (ln >> 4) * 8;
    const uint32_t wfo = base + (warp & 1) * 8192 + frow * 64 + ((((ln >> 3) & 1) ^ ((frow >> 1) & 3)) << 4);
#define LOAD_WF(m) _Pragma("unroll") for (int f = 0; f < 16; f++) {                                                   \
      const int r = ((f >> 1) * 4 + (m) * 2 + (f & 1)) * 4;                                                           \
      ldmatrix4t(((wfo + unit_of((m) ? FT_U : FT_G, warp >> 1)) ^ ((f & 1) * 32)) + (f >> 1) * 1024, wf[r], wf[r + 1], wf[r + 2], wf[r + 3]); \
    }
    bool early;
    {
#pragma unroll
      for (int i = 0; i < 16; i += 2) stmatrix4((trow ^ ((i & 7) << 4)) + (i >> 3) * 16384, xr[2 * i], xr[2 * i + 1], xr[2 * i + 2], xr[2 * i + 3]);
      const uint4 cst = lds4(par + PAR_CONST);
      const float A1 = __uint_as_float(cst.x), A2 = __uint_as_float(cst.z);
      uint32_t n = 0;
      early = false;
#pragma unroll 1
      while (true) {
        uint32_t miss;
        asm volatile("{ .reg .pred p0, p1, p2, p3; .reg .b64 u, v; .reg .b128 w;\n"
                     "setp.ge.u32 p0, %22, 2; setp.ne.and.u32 p0, %4, %21, p0; setp.ne.u32 p1, %8, %21; setp.ne.u32 p2, %12, %21; setp.ne.u32 p3, %16, %21;\n"
                     "@p0 ld.relaxed.gpu.global.v4.u32 {%1, %2, %3, %4}, [%17];\n"
                     "@p1 ld.relaxed.gpu.global.v4.u32 {%5, %6, %7, %8}, [%18];\n"
                     "@p2 ld.relaxed.gpu.global.v4.u32 {%9, %10, %11, %12}, [%19];\n"
                     "@p3 ld.relaxed.gpu.global.v4.u32 {%13, %14, %15, %16}, [%20];\n"
                     "or.pred p0, p0, p1; or.pred p2, p2, p3; or.pred p0, p0, p2; vote.sync.any.pred p0, p0, 0xffffffff; selp.u32 %0, 1, 0, p0; }"
                     : "=r"(miss), "+r"(sv[0].x), "+r"(sv[0].y), "+r"(sv[0].z), "+r"(sv[0].w), "+r"(sv[1].x), "+r"(sv[1].y), "+r"(sv[1].z), "+r"(sv[1].w),
                       "+r"(sv[2].x), "+r"(sv[2].y), "+r"(sv[2].z), "+r"(sv[2].w), "+r"(sv[3].x), "+r"(sv[3].y), "+r"(sv[3].z), "+r"(sv[3].w)
                     : "l"(sp[0]), "l"(sp[1]), "l"(sp[2]), "l"(sp[3]), "r"(tag), "r"(tq) : "memory");
        if (!miss) break;
        if (!early && (b >= NFFN || __all_sync(0xffffffffu, mbar_test(bar_box + (warp >> 1) * 8, 0)))) {
          early = true;
          LOAD_WF(0);
          __syncwarp();
          mbar_arrive_pred(bar_gate, lane0);
        }
        watchdog(n);
      }
      const uint4 v0 = tq < 2 ? own : sv[0], v1 = sv[1], v2 = sv[2], v3 = sv[3];
      PROF(8, ct == PT, 30); STAMP(6);
      float su = (__uint_as_float(v0.x) + __uint_as_float(v1.x)) + (__uint_as_float(v2.x) + __uint_as_float(v3.x));
      float sq = (__uint_as_float(v0.y) + __uint_as_float(v1.y)) + (__uint_as_float(v2.y) + __uint_as_float(v3.y));
      float dt = (__uint_as_float(v0.z) + __uint_as_float(v1.z)) + (__uint_as_float(v2.z) + __uint_as_float(v3.z));
      su += __shfl_xor_sync(0xffffffffu, su, 2); sq += __shfl_xor_sync(0xffffffffu, sq, 2); dt += __shfl_xor_sync(0xffffffffu, dt, 2);
      const float m = su * (1.f / DM);
      float mb, sd;
      ln_scalars(m, fmaxf(sq * (1.f / DM) - m * m, 0.f), mb, sd);
      const float inv = rcp(sd);
      rbest = (dt - mb * A1) * inv + A2;
      mm = pack_bf(mb, mb);
      ih = pack_bf(inv, inv);
      const float lo = inv - bf_lo(ih);
      il = pack_bf(lo, lo);
    }
    int ibest;
    {
      const uint32_t bits = __float_as_uint(rbest);
      const uint32_t key = (((int)bits < 0 ? ~bits : bits | 0x80000000u) & ~0x1ffu) | ((127 - lrow0 - (tq & 1) * 8) << 2) | tag;
      sts1(par + PAR_RED + warp * 4, __reduce_max_sync(0xffffffffu, key));
      PROF(8, ct == PT, 38); STAMP(7);
      bar_sync(1, 256);
      const uint4 ka = lds4(par + PAR_RED), kb = lds4(par + PAR_RED + 16);
      const uint32_t k2 = max(max(max(ka.x, ka.y), max(ka.z, ka.w)), max(max(kb.x, kb.y), max(kb.z, kb.w)));
      if (ct == 0 && cj == 0) st_relaxed(g_cand + rb, k2);
      ibest = 127 - ((k2 >> 2) & 127);
    }
    PROF(8, ct == PT, 39); STAMP(8);
    if ((ibest >> 4) == warp) {
      const int src = (ibest & 7) * 4 + ((ibest >> 3) & 1), ch = g * 2;
      const uint32_t cm = __shfl_sync(0xffffffffu, mm, src), ch_ = __shfl_sync(0xffffffffu, ih, src), cl = __shfl_sync(0xffffffffu, il, src);
      const uint32_t xa = res + (ch >> 3) * 16384 + ibest * 128 + (((ch & 7) ^ (ibest & 7)) << 4) + tq * 4;
      const uint32_t x0 = lds1(xa), x1 = lds1(xa ^ 16);
      const uint2 p0 = lds2(par + PAR_T2 + ch * 64 + tq * 16), p1 = lds2(par + PAR_T2 + ch * 64 + 64 + tq * 16);
      uint32_t* dst = g_row + rb * 2 * DM + cj * 128 + ln * 4;
      st_pairs(dst, ln_mod(x0, cm, ch_, cl, p0.x, p0.y), ln_mod(x1, cm, ch_, cl, p1.x, p1.y), tag);
      st_pairs(dst + DM, x0, x1, tag);
      __syncwarp();
    }
    PROF(8, ct == PT, 37); STAMP(9);
    uint32_t wd[64];
    const uint32_t wda = base + unit_of(FT_D, warp >> 1) + (warp & 1) * 8192 + frow * 128 + ((((ln >> 3) & 1) ^ (ln & 7)) << 4);
#define LOAD_WD(f) ldmatrix4t((wda ^ ((((f) >> 1) & 3) * 32)) + ((f) >> 3) * 4096 + ((f) & 1) * 2048, wd[4 * (f)], wd[4 * (f) + 1], wd[4 * (f) + 2], wd[4 * (f) + 3])
    if (!early) {
      if (b < NFFN) mbar_wait(bar_box + (warp >> 1) * 8, 0);
      LOAD_WF(0);
      __syncwarp();
      mbar_arrive_pred(bar_gate, lane0);
    }
    if (b < NFFN) {
      const uint32_t own = base + unit_of(FT_G, warp >> 1) + (warp & 1) * 8192;
      mbar_wait(bar_box + (4 + (warp >> 1)) * 8, 0);
      LOAD_WF(1);
      uint32_t* const ydst = g_ypart + ((size_t)(warp * 16 + tq * 2) * NFFN + b) * 8 + g;
      PROF(8, ct == PT, 31); STAMP(10);
      bool wdok;
      {
        uint32_t n = 0;
        while (!(wdok = __all_sync(0xffffffffu, mbar_test(bar_box + (8 + (warp >> 1)) * 8, 0))) && !__all_sync(0xffffffffu, mbar_test(bar_sel, 0))) watchdog(n);
      }
      if (wdok) {
#pragma unroll
        for (int f = 0; f < 16; f++) LOAD_WD(f);
      }
      STAMP(11);
      mbar_wait(bar_sel, 0);
      PROF(8, ct == PT, 33); STAMP(12);
      float d[8][4];
#pragma unroll
      for (int i = 0; i < 4; i++) { d[i][0] = 0.f; d[i][1] = 0.f; d[i][2] = 0.f; d[i][3] = 0.f; }
#pragma unroll
      for (int ks = 0; ks < 8; ks++) {
        const uint2 hb = lds2(own + 256 + ks * 32 + tq * 8);
#pragma unroll
        for (int mt = 0; mt < 4; mt++) {
          const int r = ks * 16 + mt * 4;
          mma16816(d[mt], wf[r], wf[r + 1], wf[r + 2], wf[r + 3], hb.x, hb.y);
        }
      }
      sts2(own + (tq * 8 + g) * 8, __float_as_uint((tq & 2) ? ((tq & 1) ? d[1][2] : d[1][0]) : ((tq & 1) ? d[0][2] : d[0][0])),
           __float_as_uint((tq & 2) ? ((tq & 1) ? d[3][2] : d[3][0]) : ((tq & 1) ? d[2][2] : d[2][0])));
      bar_sync(1, 256);
      uint32_t ab[4];
      {
        float G = 0.f, U = 0.f;
        uint2 pv[8];
#pragma unroll
        for (int w8 = 0; w8 < 8; w8++) pv[w8] = lds2(base + ln * 8 + ((FT_G >> (w8 >> 1) * 4) & 15) * UNIT + (w8 & 1) * 8192);
#pragma unroll
        for (int w8 = 0; w8 < 8; w8 += 2) {
          G += __uint_as_float(pv[w8].x) + __uint_as_float(pv[w8 + 1].x);
          U += __uint_as_float(pv[w8].y) + __uint_as_float(pv[w8 + 1].y);
        }
        const float act = rbf(silu_f(rbf(G))) * rbf(U);
        const uint32_t pk = pack_bf(act, __shfl_down_sync(0xffffffffu, act, 1));
#pragma unroll
        for (int i = 0; i < 4; i++) ab[i] = __shfl_sync(0xffffffffu, pk, i * 8 + tq * 2);
      }
      if (!wdok) {
        mbar_wait(bar_box + (8 + (warp >> 1)) * 8, 0);
#pragma unroll
        for (int f = 0; f < 16; f++) LOAD_WD(f);
      }
      PROF(8, ct == PT, 34); STAMP(13);
#pragma unroll
      for (int mt = 0; mt < 8; mt++) {
        d[mt][0] = 0.f; d[mt][1] = 0.f; d[mt][2] = 0.f; d[mt][3] = 0.f;
        mma16816(d[mt], wd[mt * 8], wd[mt * 8 + 1], wd[mt * 8 + 2], wd[mt * 8 + 3], ab[0], ab[1]);
        mma16816(d[mt], wd[mt * 8 + 4], wd[mt * 8 + 5], wd[mt * 8 + 6], wd[mt * 8 + 7], ab[2], ab[3]);
      }
#pragma unroll
      for (int i = 0; i < 4; i++) {
        const int m4 = (i >> 1) * 4, e = (i & 1) * 2;
        const float y = (tq & 2) ? ((tq & 1) ? d[m4 + 3][e] : d[m4 + 2][e]) : ((tq & 1) ? d[m4 + 1][e] : d[m4][e]);
        st_relaxed(ydst + (m4 * 2 + (i & 1)) * NFFN * 8, tagf(y, tag));
      }
      PROF(8, ct == PT, 35); STAMP(14);
    }
    mbar_wait(bar_sel, 0);
    mbar_arrive_pred(bar_win, ct == 0);
    const int iwin = lds1(par + PAR_CONST + 60) & 0x7ff;
    const bool cand = (iwin >> 4) == rb * 8 + warp;
    {
      const uint32_t mm0 = __shfl_sync(0xffffffffu, mm, ln & ~1), mm1 = __shfl_sync(0xffffffffu, mm, ln | 1);
      const uint32_t ih0 = __shfl_sync(0xffffffffu, ih, ln & ~1), ih1 = __shfl_sync(0xffffffffu, ih, ln | 1);
      const uint32_t il0 = __shfl_sync(0xffffffffu, il, ln & ~1), il1 = __shfl_sync(0xffffffffu, il, ln | 1);
#pragma unroll 1
      for (int hf = 0; hf < 2; hf++) {
        uint32_t x[16];
#pragma unroll
        for (int i = 0; i < 8; i += 2) ldmatrix4((trow ^ (i << 4)) + hf * 16384, x[2 * i], x[2 * i + 1], x[2 * i + 2], x[2 * i + 3]);
#pragma unroll
        for (int i = 0; i < 8; i++) {
          const uint4 pv = lds4(par + PAR_T2 + (hf * 8 + i) * 64 + tq * 16);
          x[2 * i] = hadd2(x[2 * i], hmul2(pv.z, ln_mod(x[2 * i], mm0, ih0, il0, pv.x, pv.y)));
          x[2 * i + 1] = hadd2(x[2 * i + 1], hmul2(pv.z, ln_mod(x[2 * i + 1], mm1, ih1, il1, pv.x, pv.y)));
        }
#pragma unroll
        for (int i = 0; i < 8; i += 2) stmatrix4((trow ^ (i << 4)) + hf * 16384, x[2 * i], x[2 * i + 1], x[2 * i + 2], x[2 * i + 3]);
      }
      if (!cand) fence_async_smem();
      __syncwarp();
      if (!cand && elect_one()) {
        tma2d_store(&maps.out, res + warp * 2048, cj * 128, rb * 128 + warp * 16);
        tma2d_store(&maps.out, res + 16384 + warp * 2048, cj * 128 + 64, rb * 128 + warp * 16);
        asm volatile("cp.async.bulk.commit_group;" ::: "memory");
      }
    }
    if (cand) {
      const int wrow0 = warp * 16;
#pragma unroll 2
      for (int p = 0; p < 8; p++) {
        const int row = 2 * p + (ln >> 4), ch = ln & 15;
        const uint4 v = lds4(res + (ch >> 3) * 16384 + (wrow0 + row) * 128 + (((ch & 7) ^ (row & 7)) << 4));
        if (rb * 128 + wrow0 + row != iwin) *reinterpret_cast<uint4*>(P.out + (size_t)(rb * 128 + wrow0 + row) * DM + cj * 128 + ch * 8) = v;
      }
    }
    asm volatile("cp.async.bulk.wait_group.read 0;" ::: "memory");
    PROF(8, ct == PT, 11); STAMP(15);
    cluster_wait();
  }
}

typedef CUresult (*EncodeFn)(CUtensorMap*, CUtensorMapDataType, cuuint32_t, void*, const cuuint64_t*, const cuuint64_t*,
                             const cuuint32_t*, const cuuint32_t*, CUtensorMapInterleave, CUtensorMapSwizzle,
                             CUtensorMapL2promotion, CUtensorMapFloatOOBfill);

void map2d(EncodeFn enc, CUtensorMap* m, const void* p, uint64_t rows, uint64_t cols, uint32_t brows) {
  cuuint64_t dims[2] = {cols, rows}, strides[1] = {cols * 2};
  cuuint32_t box[2] = {64, brows}, es[2] = {1, 1};
  enc(m, CU_TENSOR_MAP_DATA_TYPE_BFLOAT16, 2, const_cast<void*>(p), dims, strides, box, es, CU_TENSOR_MAP_INTERLEAVE_NONE,
      CU_TENSOR_MAP_SWIZZLE_128B, CU_TENSOR_MAP_L2_PROMOTION_L2_256B, CU_TENSOR_MAP_FLOAT_OOB_FILL_NONE);
}
void map2d_narrow(EncodeFn enc, CUtensorMap* m, const void* p, uint64_t rows, uint64_t cols, uint32_t brows) {
  cuuint64_t dims[2] = {cols, rows}, strides[1] = {cols * 2};
  cuuint32_t box[2] = {32, brows}, es[2] = {1, 1};
  enc(m, CU_TENSOR_MAP_DATA_TYPE_BFLOAT16, 2, const_cast<void*>(p), dims, strides, box, es, CU_TENSOR_MAP_INTERLEAVE_NONE,
      CU_TENSOR_MAP_SWIZZLE_64B, CU_TENSOR_MAP_L2_PROMOTION_L2_64B, CU_TENSOR_MAP_FLOAT_OOB_FILL_NONE);
}
void map3d(EncodeFn enc, CUtensorMap* m, const void* p, uint64_t rows, uint64_t cols, uint32_t brows, uint32_t nch) {
  cuuint64_t dims[3] = {64, rows, cols / 64}, strides[2] = {cols * 2, 128};
  cuuint32_t box[3] = {64, brows, nch}, es[3] = {1, 1, 1};
  enc(m, CU_TENSOR_MAP_DATA_TYPE_BFLOAT16, 3, const_cast<void*>(p), dims, strides, box, es, CU_TENSOR_MAP_INTERLEAVE_NONE,
      CU_TENSOR_MAP_SWIZZLE_128B, CU_TENSOR_MAP_L2_PROMOTION_L2_256B, CU_TENSOR_MAP_FLOAT_OOB_FILL_NONE);
}

}

extern "C" void kernel_launch(void* const* d_in, const int* in_sizes, int n_in, void* d_out, int out_size) {
  (void)in_sizes; (void)n_in; (void)out_size;
  static EncodeFn enc = nullptr;
  if (!enc) {
    void* fn = nullptr;
    cudaDriverEntryPointQueryResult st;
    cudaGetDriverEntryPoint("cuTensorMapEncodeTiled", &fn, cudaEnableDefault, &st);
    enc = (EncodeFn)fn;
    cudaFuncSetAttribute(fused_kernel, cudaFuncAttributeMaxDynamicSharedMemorySize, SMEM_BYTES);
  }
  Maps maps;
  map2d(enc, &maps.x, d_in[0], SEQ, DM, 128);
  map2d(enc, &maps.out, d_out, SEQ, DM, 16);
  map3d(enc, &maps.wq, d_in[3], DM, NQ, 64, 2);
  map3d(enc, &maps.k, d_in[1], 4 * SK, 128, 128, 1);
  map3d(enc, &maps.v, d_in[2], 4 * SK, 128, 128, 1);
  map3d(enc, &maps.wo, d_in[4], NQ, DM, 64, 2);
  map2d_narrow(enc, &maps.wg, d_in[7], DM, FF, 256);
  map2d_narrow(enc, &maps.wu, d_in[8], DM, FF, 256);
  map3d(enc, &maps.wd, d_in[9], FF, DM, 32, 4);
  map2d_narrow(enc, &maps.wm, d_in[11], DM, NMOD, 256);
  Ptrs p;
  p.x = (const __nv_bfloat16*)d_in[0];
  p.w_r = (const __nv_bfloat16*)d_in[6];
  p.w_gate = (const __nv_bfloat16*)d_in[7];
  p.w_up = (const __nv_bfloat16*)d_in[8];
  p.w_down = (const __nv_bfloat16*)d_in[9];
  p.c = (const __nv_bfloat16*)d_in[10];
  p.w_mod = (const __nv_bfloat16*)d_in[11];
  p.out = (__nv_bfloat16*)d_out;
  fused_kernel<<<NMAIN + NHELP, 384, SMEM_BYTES>>>(maps, p);
}
```

```cpp
#include <cuda_runtime.h>
#include <cuda_bf16.h>
#include <cuda.h>
#include <stdint.h>
#include <type_traits>

#define HD 2
#define HDX 2
#define NRS 8
#define FPACE 3
#define GOST 20
#define WB 2
#define WN 20
#define RES0 17
#define RES1 20
#define HU 32
#define NS1 5
#define PG0 15
#define PSL 0
#define FB0 0
#define FB2 8
#define OPS 8192
#define OFL 0
#define ODS 8
#define MODUL hfma2
#define ODS1 5
#define LD1 0
#define LD2 4
#define FB1 2
#define FPB 8
#define FPACE0 2
#define HALFW 1
#define HWB 1
#define HW2 1
#define HG2 0
#define VREL 5
#define E0 3

namespace {

constexpr int SEQ = 2048, DM = 1024, NQ = 4096, SK = 2048, WIN = 512, FF = 3584, NMOD = 6144;
constexpr int NMAIN = 128, NHELP = 4, NFFN = 112;
constexpr int NSLOT = 4, SLOT_BYTES = 32768, UNIT = 16384, GST_BYTES = 3 * UNIT;
constexpr uint32_t XT1 = 0xDCBA, XT2 = 0x9687;
constexpr uint32_t WT0 = 0xA741, WT1 = 0x7420, WT2 = 0x4A20;
constexpr uint32_t AT0 = WT1, AT1 = WT2;
constexpr uint32_t QT = 0xDC9696DC;
constexpr int OFF_STAGE = 12 * UNIT;
constexpr uint32_t FT_G = 0x07B3, FT_U = 0xA628, FT_D = 0x5149;
constexpr int OFF_RES = 12 * UNIT;
constexpr int OFF_PAR = 14 * UNIT;
constexpr int OFF_BAR = OFF_PAR + 2528;
constexpr int SMEM_BYTES = OFF_BAR + 544;
static_assert(SMEM_BYTES <= 232448, "smem");

constexpr int PAR_T1 = 0;
constexpr int PAR_T2 = 512;
constexpr int PAR_CONST = 1536;
constexpr int PAR_RED = 1600;
constexpr int PAR_SINK = 2176;

struct Maps {
  CUtensorMap x, wq, k, v, wo, wg, wu, wd, wm, out;
};
struct Ptrs {
  const __nv_bfloat16 *x, *w_r, *c, *w_mod, *w_gate, *w_up, *w_down;
  __nv_bfloat16* out;
};

__device__ __align__(1024) uint8_t g_act[16 * 80 * UNIT];
__device__ __align__(128) uint32_t g_mod[NMOD];
__device__ __align__(128) uint32_t g_modp[2 * 2 * DM];
__device__ __align__(128) uint32_t g_ln1[SEQ * 4];
__device__ __align__(128) uint32_t g_cnt_h[16 * 32];
__device__ __align__(128) uint32_t g_cnt_o[128 * 32];
__device__ __align__(128) uint32_t g_xch[NMAIN * 8 * 256 * 4];
__device__ __align__(128) uint32_t g_stats[8 * SEQ * 4];
__device__ __align__(128) uint32_t g_cand[32];
__device__ __align__(128) uint32_t g_row[16 * 2 * DM];
__device__ __align__(128) uint32_t g_ypart[NMAIN * NFFN * 8];
__device__ uint32_t g_epoch;

__device__ __forceinline__ uint32_t fresh_lane() { uint32_t l; asm volatile("mov.u32 %0, %%laneid;" : "=r"(l)); return l; }
__device__ __forceinline__ uint32_t frag_offset(int warp) {
  const uint32_t l = fresh_lane();
  return ((warp & 3) * 16 + (l & 15)) * 128 + (((l >> 4) ^ (l & 7)) << 4);
}
__device__ __forceinline__ bool elect_one() {
  uint32_t p;
  asm volatile("{ .reg .pred q; elect.sync _|q, 0xffffffff; selp.u32 %0, 1, 0, q; }" : "=r"(p));
  return p;
}
__device__ __forceinline__ uint32_t smem_u32(const void* p) { return (uint32_t)__cvta_generic_to_shared(p); }
__device__ __forceinline__ void mbar_init(uint32_t bar, uint32_t cnt) {
  asm volatile("mbarrier.init.shared::cta.b64 [%0], %1;" ::"r"(bar), "r"(cnt) : "memory");
}
__device__ __forceinline__ void mbar_expect_tx(uint32_t bar, uint32_t bytes) {
  asm volatile("mbarrier.arrive.expect_tx.shared::cta.b64 _, [%0], %1;" ::"r"(bar), "r"(bytes) : "memory");
}
__device__ __forceinline__ void mbar_arrive(uint32_t bar) {
  asm volatile("mbarrier.arrive.shared::cta.b64 _, [%0];" ::"r"(bar) : "memory");
}
__device__ __forceinline__ void mbar_arrive_pred(uint32_t bar, bool p) {
  asm volatile("{ .reg .pred p; setp.ne.b32 p, %1, 0; @p mbarrier.arrive.shared::cta.b64 _, [%0]; }" ::"r"(bar), "r"((int)p) : "memory");
}
__device__ __forceinline__ void mbar_arrive_cl(uint32_t bar, uint32_t off, bool p = true) {
  asm volatile("{ .reg .pred p, q; .reg .b32 a; setp.ne.b32 q, %2, 0; setp.ne.and.b32 p, %0, 0, q; add.u32 a, %0, %1; @p mbarrier.arrive.shared::cluster.b64 _, [a]; }"
               ::"r"(bar), "r"(off), "r"((int)p) : "memory");
}
__device__ __forceinline__ uint32_t mapa(uint32_t addr, uint32_t cta) {
  uint32_t r; asm("mapa.shared::cluster.u32 %0, %1, %2;" : "=r"(r) : "r"(addr), "r"(cta)); return r;
}
__device__ __forceinline__ void cluster_arrive() { asm volatile("barrier.cluster.arrive.relaxed.aligned;" ::: "memory"); }
__device__ __forceinline__ void cluster_wait() { asm volatile("barrier.cluster.wait.aligned;" ::: "memory"); }
__device__ __forceinline__ void watchdog(uint32_t& n) {
}
__device__ __forceinline__ void mbar_wait(uint32_t bar, uint32_t parity) {
  asm volatile("{\n.reg .pred p;\nWAIT_%=:\nmbarrier.try_wait.parity.shared::cta.b64 p, [%0], %1;\n@!p bra WAIT_%=;\n}" ::"r"(bar), "r"(parity) : "memory");
}
__device__ __forceinline__ bool mbar_test(uint32_t bar, uint32_t parity) {
  uint32_t ok;
  asm volatile("{\n.reg .pred p;\nmbarrier.test_wait.parity.shared::cta.b64 p, [%1], %2;\nselp.u32 %0, 1, 0, p;\n}" : "=r"(ok) : "r"(bar), "r"(parity) : "memory");
  return ok;
}
__device__ __forceinline__ uint64_t l2_stream() {
  uint64_t f; asm("createpolicy.fractional.L2::evict_first.b64 %0, 1.0;" : "=l"(f)); return f;
}
__device__ __forceinline__ void tma2d(uint32_t dst, const CUtensorMap* m, int c0, int c1, uint32_t bar) {
  asm volatile("cp.async.bulk.tensor.2d.shared::cluster.global.mbarrier::complete_tx::bytes.L2::cache_hint [%0], [%1, {%3, %4}], [%2], %5;"
               ::"r"(dst), "l"(m), "r"(bar), "r"(c0), "r"(c1), "l"(l2_stream()) : "memory");
}
__device__ __forceinline__ void bulk_load(uint32_t dst, const void* src, uint32_t bytes, uint32_t bar) {
  asm volatile("cp.async.bulk.shared::cluster.global.mbarrier::complete_tx::bytes [%0], [%1], %2, [%3];" ::"r"(dst), "l"(src), "r"(bytes), "r"(bar) : "memory");
}
__device__ __forceinline__ void bulk_load_stream(uint32_t dst, const void* src, uint32_t bytes, uint32_t bar) {
  asm volatile("cp.async.bulk.shared::cluster.global.mbarrier::complete_tx::bytes.L2::cache_hint [%0], [%1], %2, [%3], %4;"
               ::"r"(dst), "l"(src), "r"(bytes), "r"(bar), "l"(l2_stream()) : "memory");
}
__device__ __forceinline__ void tma2d_store(const CUtensorMap* m, uint32_t src, int c0, int c1) {
  asm volatile("cp.async.bulk.tensor.2d.global.shared::cta.bulk_group [%0, {%2, %3}], [%1];" ::"l"(m), "r"(src), "r"(c0), "r"(c1) : "memory");
}
__device__ __forceinline__ void bulk_store(void* dst, uint32_t src, uint32_t bytes) {
  asm volatile("cp.async.bulk.global.shared::cta.bulk_group [%0], [%1], %2;" ::"l"(dst), "r"(src), "r"(bytes) : "memory");
}
__device__ __forceinline__ int slice_of(int i) { return HALFW ? i + ((i & 7) == 1) - ((i & 7) == 2) : i; }
__device__ __forceinline__ uint32_t unit_of(uint32_t table, uint32_t i) { return ((table >> (i * 4)) & 15) * UNIT; }
__device__ __forceinline__ void tma3d(uint32_t dst, const CUtensorMap* m, int c0, int c1, int c2, uint32_t bar) {
  asm volatile("cp.async.bulk.tensor.3d.shared::cluster.global.mbarrier::complete_tx::bytes.L2::cache_hint [%0], [%1, {%3, %4, %5}], [%2], %6;"
               ::"r"(dst), "l"(m), "r"(bar), "r"(c0), "r"(c1), "r"(c2), "l"(l2_stream()) : "memory");
}
template <bool STREAM>
__device__ __forceinline__ void tma3d_mc(uint32_t dst, const CUtensorMap* m, int c0, int c1, int c2, uint32_t bar) {
  if (STREAM)
    asm volatile("cp.async.bulk.tensor.3d.shared::cluster.global.mbarrier::complete_tx::bytes.multicast::cluster.L2::cache_hint [%0], [%1, {%3, %4, %5}], [%2], %6, %7;"
                 ::"r"(dst), "l"(m), "r"(bar), "r"(c0), "r"(c1), "r"(c2), "h"((uint16_t)3), "l"(l2_stream()) : "memory");
  else
    asm volatile("cp.async.bulk.tensor.3d.shared::cluster.global.mbarrier::complete_tx::bytes.multicast::cluster [%0], [%1, {%3, %4, %5}], [%2], %6;"
                 ::"r"(dst), "l"(m), "r"(bar), "r"(c0), "r"(c1), "r"(c2), "h"((uint16_t)3) : "memory");
}
__device__ __forceinline__ void prefetch_map(const CUtensorMap* m) {
  asm volatile("prefetch.tensormap [%0];" ::"l"(m) : "memory");
}
__device__ __forceinline__ void fence_async() { asm volatile("fence.proxy.async.global;" ::: "memory"); }
__device__ __forceinline__ void fence_async_smem() { asm volatile("fence.proxy.async.shared::cta;" ::: "memory"); }
__device__ __forceinline__ void bar_sync(int id, int n) { asm volatile("bar.sync %0, %1;" ::"r"(id), "r"(n) : "memory"); }
__device__ __forceinline__ void bar_arrive(int id, int n) { asm volatile("bar.arrive %0, %1;" ::"r"(id), "r"(n) : "memory"); }
__device__ __forceinline__ void wg_fence() { asm volatile("wgmma.fence.sync.aligned;" ::: "memory"); }
__device__ __forceinline__ void wg_commit() { asm volatile("wgmma.commit_group.sync.aligned;" ::: "memory"); }
template <int N> __device__ __forceinline__ void wg_wait() { asm volatile("wgmma.wait_group.sync.aligned %0;" ::"n"(N) : "memory"); }
__device__ __forceinline__ uint64_t make_desc(uint32_t addr, uint32_t lbo, uint32_t sbo) {
  return (uint64_t)((addr & 0x3FFFF) >> 4) | ((uint64_t)(lbo >> 4) << 16) | ((uint64_t)(sbo >> 4) << 32) | (1ull << 62);
}
__device__ __forceinline__ uint32_t ld_relaxed(const uint32_t* p) {
  uint32_t v; asm volatile("ld.relaxed.gpu.global.u32 %0, [%1];" : "=r"(v) : "l"(p) : "memory"); return v;
}
__device__ __forceinline__ uint32_t ld_acquire(const uint32_t* p) {
  uint32_t v; asm volatile("ld.acquire.gpu.global.u32 %0, [%1];" : "=r"(v) : "l"(p) : "memory"); return v;
}
__device__ __forceinline__ uint4 ld_relaxed4(const uint32_t* p) {
  uint4 v; asm volatile("ld.relaxed.gpu.global.v4.u32 {%0,%1,%2,%3}, [%4];" : "=r"(v.x), "=r"(v.y), "=r"(v.z), "=r"(v.w) : "l"(p) : "memory"); return v;
}
__device__ __forceinline__ uint2 ld_relaxed2(const uint32_t* p) {
  uint2 v; asm volatile("ld.relaxed.gpu.global.v2.u32 {%0,%1}, [%2];" : "=r"(v.x), "=r"(v.y) : "l"(p) : "memory"); return v;
}
__device__ __forceinline__ void st_relaxed(uint32_t* p, uint32_t v) {
  asm volatile("st.relaxed.gpu.global.u32 [%0], %1;" ::"l"(p), "r"(v) : "memory");
}
__device__ __forceinline__ void st_relaxed2(uint32_t* p, uint32_t a, uint32_t b) {
  asm volatile("st.relaxed.gpu.global.v2.u32 [%0], {%1,%2};" ::"l"(p), "r"(a), "r"(b) : "memory");
}
__device__ __forceinline__ void st_relaxed4(uint32_t* p, uint32_t a, uint32_t b, uint32_t c, uint32_t d) {
  asm volatile("st.relaxed.gpu.global.v4.u32 [%0], {%1,%2,%3,%4};" ::"l"(p), "r"(a), "r"(b), "r"(c), "r"(d) : "memory");
}
__device__ __forceinline__ void st_b128(uint32_t* p, uint32_t a, uint32_t b, uint32_t c, uint32_t d) {
  asm volatile("{ .reg .b64 u, v; .reg .b128 w; mov.b64 u, {%1, %2}; mov.b64 v, {%3, %4}; mov.b128 w, {u, v}; st.relaxed.gpu.global.b128 [%0], w; }"
               ::"l"(p), "r"(a), "r"(b), "r"(c), "r"(d) : "memory");
}
__device__ __forceinline__ uint4 ld_b128(const uint32_t* p) {
  uint4 r;
  asm volatile("{ .reg .b64 u, v; .reg .b128 w; ld.relaxed.gpu.global.b128 w, [%4]; mov.b128 {u, v}, w; mov.b64 {%0, %1}, u; mov.b64 {%2, %3}, v; }"
               : "=r"(r.x), "=r"(r.y), "=r"(r.z), "=r"(r.w) : "l"(p) : "memory");
  return r;
}
__device__ __forceinline__ void st_pairs(uint32_t* p, uint32_t a, uint32_t b, uint32_t tag) {
  asm volatile("{ .reg .b64 u, v; mov.b64 u, {%1, %3}; mov.b64 v, {%2, %3}; st.relaxed.gpu.global.v2.b64 [%0], {u, v}; }"
               ::"l"(p), "r"(a), "r"(b), "r"(tag) : "memory");
}
__device__ __forceinline__ uint4 ld_pairs(const uint32_t* p) {
  uint4 v;
  asm volatile("{ .reg .b64 u, v; ld.relaxed.gpu.global.v2.b64 {u, v}, [%4]; mov.b64 {%0, %1}, u; mov.b64 {%2, %3}, v; }"
               : "=r"(v.x), "=r"(v.y), "=r"(v.z), "=r"(v.w) : "l"(p) : "memory");
  return v;
}
__device__ __forceinline__ uint2 ld_pair(const uint32_t* p) {
  uint2 v;
  asm volatile("{ .reg .b64 u; ld.relaxed.gpu.global.b64 u, [%2]; mov.b64 {%0, %1}, u; }" : "=r"(v.x), "=r"(v.y) : "l"(p) : "memory");
  return v;
}
__device__ __forceinline__ void red_release(uint32_t* p, uint32_t v) {
  asm volatile("red.release.gpu.global.add.u32 [%0], %1;" ::"l"(p), "r"(v) : "memory");
}
__device__ __forceinline__ uint32_t ldg_nc1(const void* p) {
  uint32_t v;
  asm volatile("ld.global.nc.u32 %0, [%1];" : "=r"(v) : "l"(p));
  return v;
}
__device__ __forceinline__ uint4 ldg_nc4(const void* p) {
  uint4 v; asm volatile("ld.global.nc.L1::no_allocate.v4.u32 {%0,%1,%2,%3}, [%4];" : "=r"(v.x), "=r"(v.y), "=r"(v.z), "=r"(v.w) : "l"(p)); return v;
}
__device__ __forceinline__ uint4 ldg_stream4(const void* p) {
  uint4 v;
  asm volatile("ld.global.nc.L1::no_allocate.L2::cache_hint.v4.u32 {%0,%1,%2,%3}, [%4], %5;" : "=r"(v.x), "=r"(v.y), "=r"(v.z), "=r"(v.w) : "l"(p), "l"(l2_stream()));
  return v;
}
__device__ __forceinline__ void stg4(void* p, uint4 v) {
  asm volatile("st.global.v4.u32 [%0], {%1,%2,%3,%4};" ::"l"(p), "r"(v.x), "r"(v.y), "r"(v.z), "r"(v.w) : "memory");
}
__device__ __forceinline__ void wait_counter(const uint32_t* p, uint32_t target) {
  uint32_t n = 0;
  while (__any_sync(0xffffffffu, (int)(ld_acquire(p) - target) < 0)) { watchdog(n); }
}
__device__ __forceinline__ uint32_t tagf(float v, uint32_t tag) { return (__float_as_uint(v) & ~3u) | tag; }
__device__ __forceinline__ bool tag_ok(uint4 v, uint32_t tag) { return (((v.x ^ tag) | (v.y ^ tag) | (v.z ^ tag) | (v.w ^ tag)) & 3u) == 0; }
__device__ __forceinline__ float untag_sum(uint32_t a, uint32_t b) { return __uint_as_float(a & ~3u) + __uint_as_float(b & ~3u); }
__device__ __forceinline__ uint4 poll4(const uint32_t* p, uint32_t tag) {
  uint4 v = ld_relaxed4(p);
  uint32_t n = 0;
  while (!__all_sync(0xffffffffu, tag_ok(v, tag))) { v = ld_relaxed4(p); watchdog(n); }
  return v;
}
__device__ __forceinline__ float bf_lo(uint32_t v) { return __uint_as_float(v << 16); }
__device__ __forceinline__ float bf_hi(uint32_t v) { return __uint_as_float(v & 0xffff0000u); }
__device__ __forceinline__ uint32_t pack_bf(float lo, float hi) {
  uint32_t r; asm("cvt.rn.bf16x2.f32 %0, %1, %2;" : "=r"(r) : "f"(hi), "f"(lo)); return r;
}
__device__ __forceinline__ float rbf(float v) { return __uint_as_float(pack_bf(0.f, v) & 0xffff0000u); }
__device__ __forceinline__ uint32_t hmul2(uint32_t a, uint32_t b) {
  uint32_t r; asm("mul.rn.bf16x2 %0, %1, %2;" : "=r"(r) : "r"(a), "r"(b)); return r;
}
__device__ __forceinline__ uint32_t hadd2(uint32_t a, uint32_t b) {
  uint32_t r; asm("add.rn.bf16x2 %0, %1, %2;" : "=r"(r) : "r"(a), "r"(b)); return r;
}
__device__ __forceinline__ uint32_t hsub2(uint32_t a, uint32_t b) {
  uint32_t r; asm("sub.rn.bf16x2 %0, %1, %2;" : "=r"(r) : "r"(a), "r"(b)); return r;
}
__device__ __forceinline__ uint32_t hmax2(uint32_t a, uint32_t b) {
  uint32_t r; asm("max.bf16x2 %0, %1, %2;" : "=r"(r) : "r"(a), "r"(b)); return r;
}
__device__ __forceinline__ float rcp(float x) { float r; asm("rcp.approx.ftz.f32 %0, %1;" : "=f"(r) : "f"(x)); return r; }
__device__ __forceinline__ float ex2(float x) { float r; asm("ex2.approx.ftz.f32 %0, %1;" : "=f"(r) : "f"(x)); return r; }
__device__ __forceinline__ void stmatrix4(uint32_t addr, uint32_t a, uint32_t b, uint32_t c, uint32_t d) {
  asm volatile("stmatrix.sync.aligned.m8n8.x4.shared.b16 [%0], {%1,%2,%3,%4};" ::"r"(addr), "r"(a), "r"(b), "r"(c), "r"(d) : "memory");
}
__device__ __forceinline__ void ldmatrix4(uint32_t addr, uint32_t& a, uint32_t& b, uint32_t& c, uint32_t& d) {
  asm volatile("ldmatrix.sync.aligned.m8n8.x4.shared.b16 {%0,%1,%2,%3}, [%4];" : "=r"(a), "=r"(b), "=r"(c), "=r"(d) : "r"(addr) : "memory");
}
__device__ __forceinline__ void ldmatrix4t(uint32_t addr, uint32_t& a, uint32_t& b, uint32_t& c, uint32_t& d) {
  asm volatile("ldmatrix.sync.aligned.m8n8.x4.trans.shared.b16 {%0,%1,%2,%3}, [%4];" : "=r"(a), "=r"(b), "=r"(c), "=r"(d) : "r"(addr) : "memory");
}
__device__ __forceinline__ void mma16816(float (&d)[4], uint32_t a0, uint32_t a1, uint32_t a2, uint32_t a3, uint32_t b0, uint32_t b1) {
  asm volatile("mma.sync.aligned.m16n8k16.row.col.f32.bf16.bf16.f32 {%0,%1,%2,%3}, {%4,%5,%6,%7}, {%8,%9}, {%0,%1,%2,%3};"
               : "+f"(d[0]), "+f"(d[1]), "+f"(d[2]), "+f"(d[3]) : "r"(a0), "r"(a1), "r"(a2), "r"(a3), "r"(b0), "r"(b1));
}
__device__ __forceinline__ void sts1(uint32_t a, uint32_t v) { asm volatile("st.shared.u32 [%0], %1;" ::"r"(a), "r"(v) : "memory"); }
__device__ __forceinline__ uint4 lds4(uint32_t a) {
  uint4 v; asm volatile("ld.shared.v4.u32 {%0,%1,%2,%3}, [%4];" : "=r"(v.x), "=r"(v.y), "=r"(v.z), "=r"(v.w) : "r"(a) : "memory"); return v;
}
__device__ __forceinline__ uint2 lds2(uint32_t a) {
  uint2 v; asm volatile("ld.shared.v2.u32 {%0,%1}, [%2];" : "=r"(v.x), "=r"(v.y) : "r"(a) : "memory"); return v;
}
__device__ __forceinline__ uint32_t lds1(uint32_t a) {
  uint32_t v; asm volatile("ld.shared.u32 %0, [%1];" : "=r"(v) : "r"(a) : "memory"); return v;
}
__device__ __forceinline__ void sts2(uint32_t a, uint32_t x, uint32_t y) { asm volatile("st.shared.v2.u32 [%0], {%1,%2};" ::"r"(a), "r"(x), "r"(y) : "memory"); }
__device__ __forceinline__ void sts4(uint32_t a, uint4 v) {
  asm volatile("st.shared.v4.u32 [%0], {%1,%2,%3,%4};" ::"r"(a), "r"(v.x), "r"(v.y), "r"(v.z), "r"(v.w) : "memory");
}
__device__ __forceinline__ float silu_f(float v) { return __fdividef(v, 1.f + __expf(-v)); }
__device__ __forceinline__ uint32_t hfma2(uint32_t a, uint32_t b, uint32_t c) {
  uint32_t r; asm("fma.rn.bf16x2 %0, %1, %2, %3;" : "=r"(r) : "r"(a), "r"(b), "r"(c)); return r;
}
__device__ __forceinline__ void split_inv(float sd, uint32_t& ih, uint32_t& il) {
  const float inv = rcp(sd);
  ih = pack_bf(inv, inv);
  const float lo = inv - bf_lo(ih);
  il = pack_bf(lo, lo);
}
__device__ __forceinline__ uint32_t ln_norm(uint32_t x, uint32_t mean2, uint32_t ih, uint32_t il) {
  const uint32_t d = hsub2(x, mean2);
  return hfma2(d, ih, hmul2(d, il));
}
__device__ __forceinline__ uint32_t modul(uint32_t n, uint32_t c1, uint32_t sh) { return hadd2(hmul2(n, c1), sh); }
__device__ __forceinline__ uint32_t ln_mod(uint32_t x, uint32_t mean2, uint32_t ih, uint32_t il, uint32_t c1, uint32_t sh) {
  return modul(ln_norm(x, mean2, ih, il), c1, sh);
}

#define R8(a, i) "+f"(a[i]), "+f"(a[i + 1]), "+f"(a[i + 2]), "+f"(a[i + 3]), "+f"(a[i + 4]), "+f"(a[i + 5]), "+f"(a[i + 6]), "+f"(a[i + 7])
#define D64 "{%0,%1,%2,%3,%4,%5,%6,%7,%8,%9,%10,%11,%12,%13,%14,%15,%16,%17,%18,%19,%20,%21,%22,%23,%24,%25,%26,%27,%28,%29,%30,%31," \
            "%32,%33,%34,%35,%36,%37,%38,%39,%40,%41,%42,%43,%44,%45,%46,%47,%48,%49,%50,%51,%52,%53,%54,%55,%56,%57,%58,%59,%60,%61,%62,%63}"
template <int TB>
__device__ __forceinline__ void mma_ss(float (&d)[64], uint64_t da, uint64_t db, int sc) {
  asm volatile("{\n.reg .pred p;\nsetp.ne.b32 p, %66, 0;\n"
               "wgmma.mma_async.sync.aligned.m64n128k16.f32.bf16.bf16 " D64 ", %64, %65, p, 1, 1, 0, %67;\n}"
               : R8(d, 0), R8(d, 8), R8(d, 16), R8(d, 24), R8(d, 32), R8(d, 40), R8(d, 48), R8(d, 56)
               : "l"(da), "l"(db), "r"(sc), "n"(TB));
}
template <int TB>
__device__ __forceinline__ void mma_rs(float (&d)[64], uint32_t a0, uint32_t a1, uint32_t a2, uint32_t a3, uint64_t db, int sc) {
  asm volatile("{\n.reg .pred p;\nsetp.ne.b32 p, %69, 0;\n"
               "wgmma.mma_async.sync.aligned.m64n128k16.f32.bf16.bf16 " D64 ", {%64,%65,%66,%67}, %68, p, 1, 1, %70;\n}"
               : R8(d, 0), R8(d, 8), R8(d, 16), R8(d, 24), R8(d, 32), R8(d, 40), R8(d, 48), R8(d, 56)
               : "r"(a0), "r"(a1), "r"(a2), "r"(a3), "l"(db), "r"(sc), "n"(TB));
}
#define D128 "{%0,%1,%2,%3,%4,%5,%6,%7,%8,%9,%10,%11,%12,%13,%14,%15,%16,%17,%18,%19,%20,%21,%22,%23,%24,%25,%26,%27,%28,%29,%30,%31," \
             "%32,%33,%34,%35,%36,%37,%38,%39,%40,%41,%42,%43,%44,%45,%46,%47,%48,%49,%50,%51,%52,%53,%54,%55,%56,%57,%58,%59,%60,%61,%62,%63," \
             "%64,%65,%66,%67,%68,%69,%70,%71,%72,%73,%74,%75,%76,%77,%78,%79,%80,%81,%82,%83,%84,%85,%86,%87,%88,%89,%90,%91,%92,%93,%94,%95," \
             "%96,%97,%98,%99,%100,%101,%102,%103,%104,%105,%106,%107,%108,%109,%110,%111,%112,%113,%114,%115,%116,%117,%118,%119,%120,%121,%122,%123,%124,%125,%126,%127}"
#define R128(d, e) R8(d, 0), R8(d, 8), R8(d, 16), R8(d, 24), R8(d, 32), R8(d, 40), R8(d, 48), R8(d, 56), \
                   R8(e, 0), R8(e, 8), R8(e, 16), R8(e, 24), R8(e, 32), R8(e, 40), R8(e, 48), R8(e, 56)
__device__ __forceinline__ void mma256_ss(float (&d)[64], float (&e)[64], uint64_t da, uint64_t db, int sc) {
  asm volatile("{\n.reg .pred p;\nsetp.ne.b32 p, %130, 0;\n"
               "wgmma.mma_async.sync.aligned.m64n256k16.f32.bf16.bf16 " D128 ", %128, %129, p, 1, 1, 0, 1;\n}"
               : R128(d, e) : "l"(da), "l"(db), "r"(sc));
}
__device__ __forceinline__ void mma256_rs(float (&d)[64], float (&e)[64], uint32_t a0, uint32_t a1, uint32_t a2, uint32_t a3, uint64_t db) {
  asm volatile("{\n.reg .pred p;\nsetp.ne.b32 p, 1, 0;\n"
               "wgmma.mma_async.sync.aligned.m64n256k16.f32.bf16.bf16 " D128 ", {%128,%129,%130,%131}, %132, p, 1, 1, 1;\n}"
               : R128(d, e) : "r"(a0), "r"(a1), "r"(a2), "r"(a3), "l"(db));
}
template <int N> __device__ __forceinline__ void keep(float (&a)[N]) {
#pragma unroll
  for (int i = 0; i < N; i++) asm volatile("" : "+f"(a[i])::"memory");
}
template <int N> __device__ __forceinline__ void keep(uint32_t (&a)[N]) {
#pragma unroll
  for (int i = 0; i < N; i++) asm volatile("" : "+r"(a[i])::"memory");
}

#define STAMP(idx) do {} while (0)
#define PROF(grp, cond, idx) do {} while (0)

constexpr float SCL2 = 1.4426950408889634f * 0.08838834764831845f;

__device__ __forceinline__ void pack_p(const float (&s)[64], uint32_t (&p)[32]) {
#pragma unroll
  for (int i = 0; i < 32; i++) p[i] = pack_bf(s[2 * i], s[2 * i + 1]);
}

__device__ __forceinline__ void issue_qk(float (&s)[64], uint32_t q0, uint32_t q1, uint32_t kslot) {
  const uint64_t db = make_desc(kslot, 16, 1024), da0 = make_desc(q0, 16, 1024), da1 = make_desc(q1, 16, 1024);
#pragma unroll
  for (int kk = 0; kk < 8; kk++) mma_ss<0>(s, (kk < 4 ? da0 : da1) + (kk & 3) * 2, db + (kk >> 2) * 1024 + (kk & 3) * 2, kk != 0);
}
__device__ __forceinline__ void issue_pv(float (&o)[64], uint32_t (&p)[32], uint32_t vslot, int acc) {
  uint64_t db = make_desc(vslot, 16384, 1024);
#pragma unroll
  for (int kk = 0; kk < 8; kk++)
    mma_rs<1>(o, p[4 * kk], p[4 * kk + 1], p[4 * kk + 2], p[4 * kk + 3], db + kk * 128, kk == 0 ? acc : 1);
}

template <int H>
__device__ __forceinline__ void store_chunk(const float (&a)[64], uint32_t addr) {
#pragma unroll
  for (int i = 8 * H; i < 8 * H + 8; i += 2)
    stmatrix4(addr ^ ((i & 7) << 4), pack_bf(a[4 * i], a[4 * i + 1]), pack_bf(a[4 * i + 2], a[4 * i + 3]),
              pack_bf(a[4 * i + 4], a[4 * i + 5]), pack_bf(a[4 * i + 6], a[4 * i + 7]));
}
template <int H>
__device__ __forceinline__ void store_chunk(const float (&a)[64], float i0, float i1, uint32_t addr) {
#pragma unroll
  for (int i = 8 * H; i < 8 * H + 8; i += 2)
    stmatrix4(addr ^ ((i & 7) << 4), pack_bf(a[4 * i] * i0, a[4 * i + 1] * i0), pack_bf(a[4 * i + 2] * i1, a[4 * i + 3] * i1),
              pack_bf(a[4 * i + 4] * i0, a[4 * i + 5] * i0), pack_bf(a[4 * i + 6] * i1, a[4 * i + 7] * i1));
}
__device__ __forceinline__ float inv_quad_sum(float l) {
  l += __shfl_xor_sync(0xffffffffu, l, 1);
  l += __shfl_xor_sync(0xffffffffu, l, 2);
  return rcp(l);
}

__device__ __forceinline__ void write_table(uint32_t table, bool ca, uint32_t t, const uint4& m0, const uint4& m1) {
  float c0 = untag_sum(m0.x, m1.x), c1 = untag_sum(m0.y, m1.y), c2 = untag_sum(m0.z, m1.z), c3 = untag_sum(m0.w, m1.w);
  if (ca) { c0 = 1.f + rbf(c0); c1 = 1.f + rbf(c1); c2 = 1.f + rbf(c2); c3 = 1.f + rbf(c3); }
  const uint32_t d = table + (t >> 2) * 64 + (t & 1) * 32 + (t & 2) * 2 + (ca ? 0 : 8);
  sts1(d, pack_bf(c0, c1));
  sts1(d + 16, pack_bf(c2, c3));
}

__device__ __forceinline__ void ln_scalars(float mean, float var, float& mb, float& sd) {
  mb = rbf(mean);
  float r; asm("sqrt.approx.ftz.f32 %0, %1;" : "=f"(r) : "f"(rbf(rbf(var) + 1e-5f)));
  sd = rbf(r);
}

__global__ void __cluster_dims__(2, 1, 1) __launch_bounds__(384, 1) fused_kernel(const __grid_constant__ Maps maps, const Ptrs P) {
  extern __shared__ __align__(1024) uint8_t smem_raw[];
  const uint32_t base = smem_u32(smem_raw);
  const int tid = threadIdx.x, lane = tid & 31;
  const int warp = __shfl_sync(0xffffffffu, tid >> 5, 0);
  const int b = blockIdx.x;
  PROF(31, tid == 0, 0);

  if (b >= NMAIN) {
    float* sc = reinterpret_cast<float*>(smem_raw);
    float* red = sc + DM;
    for (int k = tid; k < DM; k += 384) sc[k] = rbf(silu_f(__bfloat162float(P.c[k])));
    __syncthreads();
    if (tid < 256) {
      const int col = 2048 + (b - NMAIN) * 1024 + (tid & 127) * 8, r0 = (tid >> 7) * 512;
      float acc[8];
#pragma unroll
      for (int e = 0; e < 8; e++) acc[e] = 0.f;
#pragma unroll 1
      for (int r = r0; r < r0 + 512; r += HU) {
        uint4 w[HU];
#pragma unroll
        for (int u = 0; u < HU; u++) w[u] = ldg_stream4(P.w_mod + (size_t)(r + u) * NMOD + col);
#pragma unroll
        for (int u = 0; u < HU; u++) {
          float s = sc[r + u];
          acc[0] += s * bf_lo(w[u].x); acc[1] += s * bf_hi(w[u].x); acc[2] += s * bf_lo(w[u].y); acc[3] += s * bf_hi(w[u].y);
          acc[4] += s * bf_lo(w[u].z); acc[5] += s * bf_hi(w[u].z); acc[6] += s * bf_lo(w[u].w); acc[7] += s * bf_hi(w[u].w);
        }
      }
      if (tid >= 128) {
#pragma unroll
        for (int e = 0; e < 8; e++) red[(tid & 127) * 8 + e] = acc[e];
      }
      const uint32_t tag = ld_relaxed(&g_epoch) % 3 + 1;
      bar_sync(1, 256);
      if (tid < 128) {
        uint32_t o[8];
#pragma unroll
        for (int e = 0; e < 8; e++) o[e] = __float_as_uint(rbf(acc[e] + red[tid * 8 + e])) | tag;
        st_relaxed4(g_mod + col, o[0], o[1], o[2], o[3]);
        st_relaxed4(g_mod + col + 4, o[4], o[5], o[6], o[7]);
        const uint4 wr = ldg_nc4(P.w_r + tid * 8);
        const uint32_t wv[4] = {wr.x, wr.y, wr.z, wr.w};
        float dsum = 0.f;
#pragma unroll
        for (int e = 0; e < 8; e++) {
          const float m = bf_hi(o[e]);
          dsum += (b == NMAIN + 2 ? rbf(1.f + m) : m) * ((e & 1) ? bf_hi(wv[e >> 1]) : bf_lo(wv[e >> 1]));
        }
#pragma unroll
        for (int k = 16; k > 0; k >>= 1) dsum += __shfl_xor_sync(0xffffffffu, dsum, k);
        if (lane == 0) st_relaxed(g_mod + (b - NMAIN) * 4 + warp, tagf(dsum, tag));
      }
    }
    PROF(2, tid == 0, 1);
    return;
  }

  const int rank = b & 1;
  const int rb = ((b >> 4) << 1) | rank, cj = (b >> 1) & 7;
  const bool late = HALFW && (b & 4);
  const uint32_t bfull = base + OFF_BAR, bempty = bfull + NSLOT * 8;
  const uint32_t gfull = bempty + NSLOT * 8, gempty = gfull + 32;
  const uint32_t bar_ofull = gempty + 32;
  const uint32_t bar_ofree = bar_ofull + 32;
  const uint32_t bar_par = bar_ofree + 32;
  const uint32_t bar_mod = bar_par + 8;
  const uint32_t bar_pread = bar_mod + 8;
  const uint32_t bar_xres = bar_pread + 8;
  const uint32_t bar_ring = bar_xres + 8;
  const uint32_t bar_box = bar_ring + 24;
  const uint32_t bar_go = bar_box + 96;
  const uint32_t bar_go2 = bar_go + 16;
  const uint32_t bar_cnt = bar_go + 24;
  const uint32_t xfull = bar_go + 40, xempty = xfull + 32;
  const uint32_t bar_hw = xempty + 32, bar_hx = bar_hw + 8;
  const uint32_t bar_hpub = bar_hx + 16;
  const uint32_t bar_win = bar_hpub + 16;
  const uint32_t bar_rx = bar_win + 8;
  const uint32_t bar_sel = bar_rx + 8;
  const uint32_t bar_gate = bar_sel + 8;
  const uint32_t bar_rel = bar_gate + 8;
  const uint32_t bar_od = bar_rel + 8;
  const uint32_t bar_mod2 = bar_od + 8;
  const uint32_t bar_res = bar_go + 8;
  const uint32_t stage = base + OFF_STAGE, par = base + OFF_PAR;

  if (warp == 8 && elect_one()) {
    for (int s = 0; s < NSLOT; s++) { mbar_init(bfull + s * 8, 1); mbar_init(bempty + s * 8, 16); }
    for (int s = 0; s < 4; s++) { mbar_init(gfull + s * 8, 1); mbar_init(gempty + s * 8, 16); mbar_init(xfull + s * 8, 1); mbar_init(xempty + s * 8, 8); mbar_init(bar_ofree + s * 8, 1); mbar_init(bar_ofull + s * 8, 128); }
    mbar_init(bar_par, 64); mbar_init(bar_mod, 256); mbar_init(bar_pread, 2); mbar_init(bar_xres, 1);
    mbar_init(bar_ring, 8); mbar_init(bar_ring + 8, 8); mbar_init(bar_ring + 16, 8);
    mbar_init(bar_go, 1); mbar_init(bar_go2, 1); mbar_init(bar_cnt, 1); mbar_init(bar_cnt + 8, 1); mbar_init(bar_hpub, 8); mbar_init(bar_hpub + 8, 8); mbar_init(bar_res, 1); mbar_init(bar_win, 1); mbar_init(bar_rx, 1); mbar_init(bar_sel, 64); mbar_init(bar_gate, 8); mbar_init(bar_rel, 8); mbar_init(bar_od, 1); mbar_init(bar_mod2, 64);
    for (int s = 0; s < 12; s++) mbar_init(bar_box + s * 8, 1);
    asm volatile("fence.mbarrier_init.release.cluster;" ::: "memory");
    prefetch_map(&maps.x); prefetch_map(&maps.wq); prefetch_map(&maps.k); prefetch_map(&maps.v);
  }
  if (warp == 9 && elect_one()) {
    mbar_init(bar_hw, 1); mbar_init(bar_hx, 1); mbar_init(bar_hx + 8, 1);
    asm volatile("fence.mbarrier_init.release.cluster;" ::: "memory");
    mbar_expect_tx(bar_hw, 32768);
    mbar_expect_tx(bar_hx, 16384);
    mbar_expect_tx(bar_hx + 8, 16384);
    const __nv_bfloat16* xs = P.x + (size_t)(rb * 128 + cj * 16) * DM;
    bulk_load(base + 2 * GST_BYTES, xs, 16384, bar_hx);
    if (!late) {
      tma2d(stage, &maps.wm, (b >> 1) * 32, rank * 512, bar_hw);
      tma2d(stage + 16384, &maps.wm, (b >> 1) * 32, rank * 512 + 256, bar_hw);
    } else {
      prefetch_map(&maps.wm);
    }
    bulk_load(base + 3 * GST_BYTES, xs + 8 * DM, 16384, bar_hx + 8);
  }
  cluster_arrive();

  if (warp >= 8) {
    asm volatile("setmaxnreg.dec.sync.aligned.u32 40;");
    if (warp < 10) bar_arrive(1, 320);
    const uint32_t epoch = ld_relaxed(&g_epoch);
    cluster_wait();
    if (warp == 8) {
      const int kvrow = (cj >> 1) * SK + (SK - WIN);
      int wch = cj * 8 + rank * 2;
#pragma unroll 1
      for (int ps = 0; ps < 3; ps++) {
        const CUtensorMap* mw = ps == 2 ? &maps.wo : &maps.wq;
        const uint32_t xt = ps == 1 ? XT1 : XT2, wt = ps == 0 ? WT0 : (ps == 1 ? WT1 : WT2);
        const int nst = ps == 2 ? 32 : 16;
#pragma unroll 1
        for (int i = 0; i < nst; i++) {
          const uint32_t bf = gfull + (i & 3) * 8;
          const int kt = ps == 2 ? (((cj & 1) * 4 + ((i >> 1) & 3)) * 4 + (i >> 3)) * 2 + (i & 1) : (ps ? i : slice_of(i) + (b & 14)) & 15;
          const uint32_t wd = base + unit_of(wt, i & 3) + rank * UNIT, xd = base + unit_of(xt, i & 3);
          const uint8_t* xs = g_act + (uint32_t)(rb * 80 + (ps - 1) * 16 + kt) * UNIT;
          if (ps == 0 && i == HD) { mbar_wait(bar_mod, 0); if (HG2) mbar_wait(bar_mod2, 0); }
          const bool xfirst = ps && i < 2;
          if (ps == 2 && i == 0) mbar_wait(bar_ofree + 24, 0);
          if (i == 0) fence_async();
          mbar_wait(gempty + (i & 3) * 8, ((i >> 2) & 1) ^ 1);
          if (elect_one()) {
            mbar_expect_tx(bf, ps ? GST_BYTES : 2 * UNIT);
            if (xfirst) bulk_load_stream(xd, xs, UNIT, bf);
          }
          if (ps && i < 4) mbar_wait(bempty + i * 8, 1);
          if (elect_one()) tma3d_mc<true>(wd, mw, 0, (i == 31 ? kt ^ (rank * 32) : kt) * 64, i == 31 ? cj * 2 : wch, bf);
          if (ps) {
            if (i == 16 || i == 24) { mbar_wait(bar_cnt + i - 16, 0); fence_async(); }
            if (i == RES0) mbar_wait(bar_res, 0);
            if (i == 2) mbar_wait(bar_ofree + (ps - 1) * 16, 0);
            if (elect_one()) {
              if (i == 31) bulk_load(xd, xs, UNIT, bf); else if (!xfirst) bulk_load_stream(xd, xs, UNIT, bf);
              mbar_arrive_pred(bar_go, i == GOST - 1);
              if (PG0 < 16) mbar_arrive_pred(bar_go2, ps == 1 && i == PG0);
              mbar_arrive_pred(bar_od, i == (ps == 1 ? ODS1 : ODS));
              if (i == RES0) mbar_expect_tx(bar_xres, 32768);
              if (i == RES0 || i == RES1) tma2d(base + OFF_RES + (i == RES1) * UNIT, &maps.x, cj * 128 + (i == RES1) * 64, rb * 128, bar_xres);
            }
          }
        }
        if (ps == 2) break;
        wch = ps ? ((wch >> 3) ^ rank) * 2 : wch + 4;
#pragma unroll 1
        for (int u = 0; u < 16; u++) {
          const bool isk = (u == 0) || ((u & 1) && u < 15);
          const int blk = (isk ? (u + 1) >> 1 : (u == 15 ? 7 : (u >> 1) - 1)) & 3;
          const uint32_t sl = base + unit_of(ps ? AT1 : AT0, u & 3) + rank * UNIT, bf = bfull + (u & 3) * 8;
          if (u < 4) mbar_wait(gempty + ((u + 1) >> 1) * 8, 1);
          mbar_wait(bempty + (u & 3) * 8, ((u >> 2) & 1) ^ 1);
          if (elect_one()) {
            mbar_arrive_pred(bar_go2, ps && u + 16 == PG0);
            mbar_expect_tx(bf, SLOT_BYTES);
            tma3d_mc<false>(sl, isk ? &maps.k : &maps.v, 0, kvrow + blk * 128, rank, bf);
          }
        }
      }
      if (elect_one()) mbar_expect_tx(bar_rx, UNIT);
      mbar_wait(bar_rel, 0);
      if (elect_one()) {
        bulk_load_stream(base + UNIT, g_act + (uint32_t)(rb * 80 + 16 + 63 - (cj & 1) * 32) * UNIT, UNIT, bar_rx);
      }
      if (b < NFFN) {
#pragma unroll 1
        for (int u = 0; u < 12; u++) {
          const uint32_t dst = base + unit_of(u < 4 ? FT_G : (u < 8 ? FT_U : FT_D), u & 3);
          if (elect_one()) mbar_expect_tx(bar_box + u * 8, UNIT);
          if (u == FB0 || u == FB1 || u == FB2) mbar_wait(bar_ring + (u == FB2 ? 16 : u == FB1 ? 8 : 0), 0);
          const int fp = u < FPB ? FPACE0 : FPACE;
          if (u >= fp) mbar_wait(bar_box + (u - fp) * 8, 0);
          if (elect_one()) {
            if (u < 8) tma2d(dst, u < 4 ? &maps.wg : &maps.wu, b * 32, (u & 3) * 256, bar_box + u * 8);
            else tma3d(dst, &maps.wd, 0, b * 32, (u - 8) * 4, bar_box + u * 8);
          }
        }
      }
    } else if (warp == 9) {
      const uint32_t target = 8 * (epoch + 1);
      uint32_t hmask = 0;
#pragma unroll 1
      for (int i = 0; i < 16; i++) {
        if (i == HDX) { mbar_wait(bar_mod, 0); if (HG2) mbar_wait(bar_mod2, 0); }
        const int kt = (2 * cj + slice_of(i)) & 15;
        const uint32_t need = i == 15 ? 0xffffu : 1u << kt;
        if (i >= NRS && (hmask & need) != need) {
          uint32_t n = 0;
          do { hmask = __ballot_sync(0xffffffffu, ld_acquire(&g_cnt_h[rb * 32 + (lane & 15)]) == epoch + 1); watchdog(n); } while ((hmask & need) != need);
          PROF(1, lane == 0 && i == NRS, 26);
          fence_async();
        }
        mbar_wait(xempty + (i & 3) * 8, ((i >> 2) & 1) ^ 1);
        if (elect_one()) {
          mbar_expect_tx(xfull + (i & 3) * 8, UNIT);
          if (i < NRS) tma2d(base + (i & 3) * GST_BYTES, &maps.x, kt * 64, rb * 128, xfull + (i & 3) * 8);
          else bulk_load_stream(base + (i & 3) * GST_BYTES, g_act + (uint32_t)(rb * 80 + kt) * UNIT, UNIT, xfull + (i & 3) * 8);
        }
      }
      prefetch_map(&maps.wo);
#pragma unroll 1
      for (int t = 0; t < 4; t++) {
        if (t & 1) mbar_wait(bar_od, t >> 1);
#pragma unroll 1
        for (int p = 0; p < 32768 / OPS; p++) {
          const uint32_t w = p / (16384 / OPS), c = (p / (8192 / OPS)) & 1, off = w * 8192 + (p % (8192 / OPS)) * OPS;
          mbar_wait(bar_ofull + (t & 1) * 16 + w * 8, t >> 1);
          if (elect_one()) {
            bulk_store(g_act + (uint32_t)(rb * 80 + 16 + (cj * 4 + t) * 2 + c) * UNIT + off, base + unit_of(QT, 2 * t + c) + off, OPS);
            asm volatile("cp.async.bulk.commit_group;" ::: "memory");
            asm volatile("cp.async.bulk.wait_group.read %0;" ::"n"(OFL) : "memory");
          }
        }
        if (elect_one()) {
          asm volatile("cp.async.bulk.wait_group.read 0;" ::: "memory");
          mbar_arrive(t < 3 ? bar_ofree + t * 8 : bar_res);
          asm volatile("cp.async.bulk.wait_group 0;" ::: "memory");
          fence_async();
          red_release(&g_cnt_o[((rb * 4 + t) * 2 + (cj >> 2)) * 32], 2);
        }
        if (t) {
          wait_counter(&g_cnt_o[(rb * 8 + 2 * t + (cj & 1)) * 32], target);
          if (t & 1) wait_counter(&g_cnt_o[(rb * 8 + (t == 1 ? cj & 1 : 7 - (cj & 1))) * 32], target);
          if (elect_one()) mbar_arrive(t == 1 ? bar_ofree + 24 : bar_cnt + t * 8 - 16);
        }
      }
      PROF(2, lane == 0, 27);
      const uint32_t tag = epoch % 3 + 1;
      const uint32_t* inbox = g_cand + (lane & 15);
      mbar_wait(bar_ring + 16, 0);
      uint32_t c0 = ld_relaxed(inbox), n = 0;
#define CAND_STEP(cv)                                                                                        \
      {                                                                                                      \
        const bool valid = (cv & 3u) == tag, all = __all_sync(0xffffffffu, valid);                           \
        const uint32_t best = __reduce_max_sync(0xffffffffu, valid ? cv : 0u);                               \
        const uint32_t blk = __ffs(__ballot_sync(0xffffffffu, cv == best)) - 1;                              \
        if (best) sts2(par + PAR_CONST + 56, best, (blk << 7 | (~best >> 2 & 127)) | (all ? 0x1800 : 0x800)); \
        if (all) break;                                                                                      \
        cv = ld_relaxed(inbox);                                                                              \
      }
      while (true) { CAND_STEP(c0) watchdog(n); }
    } else {
      const int t2 = tid - 320;
      if (late && warp == 10) {
        mbar_wait(bar_hx + HWB * 8, 0);
        if (elect_one()) {
          tma2d(stage, &maps.wm, (b >> 1) * 32, rank * 512, bar_hw);
          tma2d(stage + 16384, &maps.wm, (b >> 1) * 32, rank * 512 + 256, bar_hw);
        }
      }
      if (HALFW && (warp == 11 || HW2)) {
        const uint32_t tag = epoch % 3 + 1;
        mbar_wait(bar_hx + 8, 0);
        mbar_wait(bar_hw, 0);
#pragma unroll 1
        for (int r = HW2 ? warp & 1 : 0; r < 2; r += HW2 ? 2 : 1) {
          const uint32_t t7 = r * 64 + (lane >> 4) * 32 + 16 + (lane & 15);
          const uint32_t* pm = g_modp + ((cj * 128 + t7 * 4) & (DM - 1));
          uint4 m0, m1, m2, m3;
          uint32_t n = 0;
          do {
            m0 = ld_relaxed4(pm); m1 = ld_relaxed4(pm + 2 * DM); m2 = ld_relaxed4(pm + DM); m3 = ld_relaxed4(pm + 3 * DM);
            watchdog(n);
          } while (!__all_sync(0xffffffffu, tag_ok(m0, tag) && tag_ok(m1, tag) && tag_ok(m2, tag) && tag_ok(m3, tag)));
          write_table(par, false, t7, m0, m1);
          write_table(par, true, t7, m2, m3);
          mbar_arrive(bar_mod2);
        }
      }
      mbar_wait(bar_hpub + (warp & 1) * 8, 0);
      PROF(1, t2 == 0, 24);
#pragma unroll 1
      for (int c = 0; c < 8; c++) {
        const uint32_t off = (warp & 1) * UNIT + c * 2048 + lane * 16;
        uint8_t* dst = g_act + (uint32_t)(rb * 80 + cj * 2) * UNIT + off;
        const uint4 v0 = lds4(stage + off), v1 = lds4(stage + off + 512), v2 = lds4(stage + off + 1024), v3 = lds4(stage + off + 1536);
        stg4(dst, v0); stg4(dst + 512, v1); stg4(dst + 1024, v2); stg4(dst + 1536, v3);
      }
      __syncwarp();
      PROF(1, t2 == 0, 15);
      if (lane == 0) {
        mbar_arrive(bar_pread);
        red_release(&g_cnt_h[rb * 32 + cj * 2 + (warp & 1)], 1);
        PROF(1, t2 == 0, 25);
        prefetch_map(&maps.wg); prefetch_map(&maps.wu); prefetch_map(&maps.wd); prefetch_map(&maps.out);
      }
      __syncwarp();
      if (b < NFFN) {
        mbar_wait(bar_go2, 0);
        const __nv_bfloat16* pg = ((b & 1) ? P.w_up : P.w_gate) + (b >> 1) * 64 + (size_t)t2 * FF;
        const __nv_bfloat16* pd = P.w_down + (size_t)b * 32768 + t2 * 64;
        PROF(2, t2 == 0, 13);
#pragma unroll 1
        for (int i = 0; i < WN; i += WB) {
          uint32_t v[WB];
#pragma unroll
          for (int u = 0; u < WB; u++) {
            const int k = i + u;
            asm volatile("ld.global.cg.L2::128B.u32 %0, [%1];" : "=r"(v[u]) : "l"(k < 16 ? pg + (size_t)k * 64 * FF : pd + (k - 16) * 4096));
          }
#pragma unroll
          for (int u = 1; u < WB; u++) v[0] ^= v[u];
          sts1(par + PAR_SINK + t2 * 4, v[0]);
        }
        PROF(2, t2 == 0, 14);
      }
      const uint32_t tag = epoch % 3 + 1;
      mbar_wait(bar_go, 0);
      bar_sync(4, 64);
      if (warp == 10) {
        const uint32_t* src = g_mod + 2 * DM + cj * 128 + lane * 4;
        const uint2 wr = *reinterpret_cast<const uint2*>(P.w_r + cj * 128 + lane * 4);
        uint4 vga, vsb, vcb, vgb;
        uint32_t n = 0;
        do {
          vga = ld_relaxed4(src); vsb = ld_relaxed4(src + DM); vcb = ld_relaxed4(src + 2 * DM); vgb = ld_relaxed4(src + 3 * DM);
          watchdog(n);
        } while (!__all_sync(0xffffffffu, tag_ok(vga, tag) && tag_ok(vsb, tag) && tag_ok(vcb, tag) && tag_ok(vgb, tag)));
        const float c0 = rbf(1.f + bf_hi(vcb.x)), c1 = rbf(1.f + bf_hi(vcb.y)), c2 = rbf(1.f + bf_hi(vcb.z)), c3 = rbf(1.f + bf_hi(vcb.w));
        const float a0 = c0 * bf_lo(wr.x), a1 = c1 * bf_hi(wr.x), a2 = c2 * bf_lo(wr.y), a3 = c3 * bf_hi(wr.y);
        const uint32_t h0 = pack_bf(a0, a1), h1 = pack_bf(a2, a3);
        const uint32_t t1 = par + PAR_T1 + (lane >> 2) * 64 + (lane & 1) * 32 + (lane & 2) * 2;
        sts1(t1, h0); sts1(t1 + 8, pack_bf(a0 - bf_lo(h0), a1 - bf_hi(h0)));
        sts1(t1 + 16, h1); sts1(t1 + 24, pack_bf(a2 - bf_lo(h1), a3 - bf_hi(h1)));
        const uint32_t tg = par + PAR_SINK + (lane >> 3) * 64 + (lane & 1) * 32 + (lane & 6) * 2;
        sts1(tg, __byte_perm(vga.x, vga.y, 0x7632)); sts1(tg + 16, __byte_perm(vga.z, vga.w, 0x7632));
        sts4(par + PAR_T2 + lane * 32, make_uint4(pack_bf(c0, c1), __byte_perm(vsb.x, vsb.y, 0x7632), __byte_perm(vgb.x, vgb.y, 0x7632), __byte_perm(vga.x, vga.y, 0x7632)));
        sts4(par + PAR_T2 + lane * 32 + 16, make_uint4(pack_bf(c2, c3), __byte_perm(vsb.z, vsb.w, 0x7632), __byte_perm(vgb.z, vgb.w, 0x7632), __byte_perm(vga.z, vga.w, 0x7632)));
      } else {
        const uint4 g = poll4((lane & 2) ? g_mod + 8 - (lane & 1) * 4 : g_mod + 5 * DM + b * 8 + (lane & 1) * 4, tag);
        sts1(par + PAR_CONST + 60, 0);
        if (lane < 2) sts4(par + PAR_CONST + 16 + lane * 16, g);
        else if (lane < 4) sts2(par + PAR_CONST + (lane - 2) * 8, __float_as_uint(untag_sum(g.x, g.y) + untag_sum(g.z, g.w)), epoch);
      }
      __syncwarp();
#pragma unroll 4
      for (int q = 0; q < 32; q++) st_b128(g_xch + ((size_t)b * 8 * 256 + q * 64 + t2) * 4, (epoch & 1) << 16, 0, 0, 0);
      for (int q = 0; q < 2; q++) st_relaxed4(g_stats + ((size_t)cj * SEQ + rb * 128 + q * 64 + t2) * 4, 0, 0, 0, 0);
      if (b < NFFN)
        for (int q = 0; q < 4; q++) st_relaxed4(g_ypart + ((size_t)(q * 32 + (t2 >> 1)) * NFFN + b) * 8 + (t2 & 1) * 4, 0, 0, 0, 0);
      st_relaxed4(g_row + rb * 2 * DM + (t2 >> 5) * DM + cj * 128 + (t2 & 31) * 4, 0, 0, 0, 0);
      __threadfence();
      mbar_arrive(bar_par);
      mbar_wait(bar_gate, 0);
      uint32_t have = 0, n = 0;
      while (true) {
        const uint32_t st = lds1(par + PAR_CONST + 60) >> 7;
        if ((st & 31) != have) {
          const uint32_t* hsrc = g_row + (st & 15) * 2 * DM + t2 * 4;
          uint4 hv[4];
          bool ok = true;
#pragma unroll
          for (int i = 0; i < 4; i++) hv[i] = ld_pairs(hsrc + i * 256);
#pragma unroll
          for (int i = 0; i < 4; i++) {
            sts2(base + ((FT_G >> i * 4) & 15) * UNIT + (warp & 1) * 8192 + 256 + lane * 8, hv[i].x, hv[i].z);
            ok = ok && hv[i].y == tag && hv[i].w == tag;
          }
          have = __all_sync(0xffffffffu, ok) ? st & 31 : 0;
        }
        if ((st ^ have) == 32) break;
        watchdog(n);
      }
      mbar_arrive(bar_sel);
    }
    __syncwarp();
    cluster_arrive();
    {
      const uint32_t tag = epoch % 3 + 1, t3 = tid - 256;
      mbar_wait(bar_win, 0);
      uint2 win = lds2(par + PAR_CONST + 56);
      win.y &= 0x7ff;
      const uint32_t* fsrc = g_row + (win.y >> 7) * 2 * DM + (b >> 1) * 16 + (t3 & 3) * 4 + (b & 1) * 2;
      const uint32_t* ysrc = g_ypart + (size_t)b * NFFN * 8 + min(t3, NFFN - 1) * 4;
      uint2 fh = ld_pair(fsrc), fx = ld_pair(fsrc + DM);
      if (PSL) __nanosleep(PSL);
      uint4 ya = ld_relaxed4(ysrc), yb = ld_relaxed4(ysrc + NFFN * 4);
      const float rwin = __uint_as_float(((int)win.x < 0 ? win.x & 0x7fffffffu : ~win.x) & ~0x1ffu);
      const float rs = rbf(rcp(1.f + __expf(-rbf(rwin))));
      uint32_t n = 0;
      while (__any_sync(0xffffffffu, fh.y != tag || fx.y != tag)) { fh = ld_pair(fsrc); fx = ld_pair(fsrc + DM); watchdog(n); }
      while (!__all_sync(0xffffffffu, tag_ok(ya, tag) && tag_ok(yb, tag))) {
        if (!tag_ok(ya, tag)) ya = ld_relaxed4(ysrc);
        if (!tag_ok(yb, tag)) yb = ld_relaxed4(ysrc + NFFN * 4);
        watchdog(n);
      }
      __syncwarp();
      PROF(8, t3 == 0, 5);
      float y0 = untag_sum(ya.x, yb.x), y1 = untag_sum(ya.y, yb.y), y2 = untag_sum(ya.z, yb.z), y3 = untag_sum(ya.w, yb.w);
      const bool u1 = lane & 2, u2 = lane & 4;
      y0 = (u1 ? y2 : y0) + __shfl_xor_sync(0xffffffffu, u1 ? y0 : y2, 2);
      y1 = (u1 ? y3 : y1) + __shfl_xor_sync(0xffffffffu, u1 ? y1 : y3, 2);
      y0 = (u2 ? y1 : y0) + __shfl_xor_sync(0xffffffffu, u2 ? y0 : y1, 4);
      y0 += __shfl_xor_sync(0xffffffffu, y0, 8);
      if (!(lane & 8)) sts1(par + PAR_RED + 64 + (t3 >> 4) * 32 + ((lane & 1) * 4 + (lane & 2) + ((lane >> 2) & 1)) * 4, __float_as_uint(y0));
      bar_sync(4, 128);
      if (t3 < 4) {
        y0 = 0.f; y1 = 0.f;
#pragma unroll
        for (int w4 = 0; w4 < 7; w4++) {
          const uint2 v = lds2(par + PAR_RED + 64 + w4 * 32 + t3 * 8);
          y0 += __uint_as_float(v.x); y1 += __uint_as_float(v.y);
        }
        const uint2 gv = lds2(par + PAR_CONST + 16 + t3 * 8);
        const uint32_t upd = hmul2(pack_bf(y0, y1), pack_bf(rs, rs));
        *reinterpret_cast<uint32_t*>(P.out + (size_t)win.y * DM + b * 8 + t3 * 2) =
            hadd2(fx.x, hmul2(__byte_perm(gv.x, gv.y, 0x7632), hadd2(fh.x, upd)));
        if (b == 0 && t3 == 0) st_relaxed(&g_epoch, epoch + 1);
      }
      PROF(31, t3 == 0, 36);
    }
    cluster_wait();
  } else {
    const int wg = warp >> 2;

    uint32_t tag;
    {
      uint32_t* const pmod = g_modp + rank * 2 * DM + (b >> 1) * 32 + lane;
      uint32_t* const pln = g_ln1 + (rb * 128 + cj * 16 + warp) * 4;
      uint32_t sc[8];
#pragma unroll
      for (int k = 0; k < 8; k++) sc[k] = ldg_nc1(P.c + rank * 512 + warp * 64 + k * 8 + (lane & 3) * 2);
      const uint32_t epoch = ld_relaxed(&g_epoch);
      if (warp == 0) st_relaxed(pmod, 0);
      if (lane == 0) { st_b128(pln, 0, 0, 0, 0); st_b128(pln + 32, 0, 0, 0, 0); }
      asm volatile("setmaxnreg.inc.sync.aligned.u32 232;");
      bar_sync(1, 320);
#pragma unroll
      for (int k = 0; k < 8; k++) sc[k] = pack_bf(silu_f(bf_lo(sc[k])), silu_f(bf_hi(sc[k])));
      keep(sc);
      tag = epoch % 3 + 1;
#pragma unroll
      for (int part = 0; part < 4; part++) {
        if (!(part & 1)) {
          const uint32_t xa = base + (2 + part / 2) * GST_BYTES + warp * 2048 + lane * 16;
          mbar_wait(bar_hx + part * 4, 0);
          float s0 = 0.f, s1 = 0.f, q0 = 0.f, q1 = 0.f;
#pragma unroll
          for (int q = 0; q < 4; q++) {
            const uint4 xv = lds4(xa + q * 512);
            const uint32_t u[4] = {xv.x, xv.y, xv.z, xv.w};
#pragma unroll
            for (int e = 0; e < 4; e++) { const float lo = bf_lo(u[e]), hi = bf_hi(u[e]); s0 += lo; s1 += hi; q0 += lo * lo; q1 += hi * hi; }
          }
          s0 += s1; q0 += q1;
#pragma unroll
          for (int o = 16; o > 0; o >>= 1) { s0 += __shfl_xor_sync(0xffffffffu, s0, o); q0 += __shfl_xor_sync(0xffffffffu, q0, o); }
          const float mean = s0 * (1.f / DM);
          float mb, sd;
          ln_scalars(mean, fmaxf(q0 * (1.f / DM) - mean * mean, 0.f), mb, sd);
          uint32_t ih, il;
          split_inv(sd, ih, il);
          if (lane == 0) st_b128(pln + part * 16, pack_bf(mb, mb), ih, il, tag);
          PROF(1, tid == 0 && part == 2, 4);
        } else if (late == (part == 3)) {
          const uint32_t fr = (lane & 7) + (lane >> 4) * 8, tq = lane & 3;
          const uint32_t wa = stage + warp * 4096 + fr * 64 + ((((lane >> 3) & 1) ^ ((fr >> 1) & 3)) << 4);
          float d0[4] = {0.f, 0.f, 0.f, 0.f}, d1[4] = {0.f, 0.f, 0.f, 0.f};
          mbar_wait(bar_hw, 0);
#pragma unroll
          for (int ks = 0; ks < 4; ks++) {
            uint32_t w[8];
            ldmatrix4t(wa + ks * 1024, w[0], w[1], w[2], w[3]);
            ldmatrix4t((wa ^ 32) + ks * 1024, w[4], w[5], w[6], w[7]);
            mma16816(d0, w[0], w[1], w[2], w[3], sc[2 * ks], sc[2 * ks + 1]);
            mma16816(d1, w[4], w[5], w[6], w[7], sc[2 * ks], sc[2 * ks + 1]);
          }
          sts1(base + 2 * GST_BYTES + warp * 2048 + (tq * 8 + (lane >> 2)) * 4, __float_as_uint((tq & 2) ? ((tq & 1) ? d1[2] : d1[0]) : ((tq & 1) ? d0[2] : d0[0])));
          bar_sync(1, 256);
          if (warp == 0) {
            float s = 0.f;
#pragma unroll
            for (int w8 = 0; w8 < 8; w8++) s += __uint_as_float(lds1(base + 2 * GST_BYTES + w8 * 2048 + lane * 4));
            st_relaxed(pmod, (__float_as_uint(s) & ~3u) | tag);
          }
          PROF(1, tid == 0, 3);
        }
      }
      cluster_wait();
      if (wg == 1) bar_arrive(2, 256);
    }

    float f0 = 0.f, f1 = 0.f;
    const uint32_t rempty = lane < 2 ? mapa(bempty, lane & 1) : 0;
    constexpr uint32_t GE = NSLOT * 8 + 32;
    float o[64], s[64];
#pragma unroll 1
    for (int ps = 0; ps < 3; ps++) {
      {
        const uint32_t xt = ps == 1 ? XT1 : XT2, wt = ps == 1 ? WT1 : WT2;
        const int nst = ps == 2 ? 28 : 14;
        if (ps == 0) {
          float ga[64], gb[64];
#pragma unroll
          for (int i = 0; i < 64; i++) { ga[i] = 0.f; gb[i] = 0.f; }
          uint32_t a[2][16];
          const uint32_t l = fresh_lane();
          uint32_t fa[4];
#pragma unroll
          for (int kk = 0; kk < 4; kk++) fa[kk] = (base + wg * 8192 + frag_offset(warp)) ^ (kk * 32);
          const uint32_t mt = par + (l & 3) * 16;
          auto fetch = [&](int i, uint32_t (&f)[16], uint32_t z) {
            mbar_wait(xfull + (i & 3) * 8, i >> 2);
#pragma unroll
            for (int kk = 0; kk < 4; kk++) ldmatrix4(fa[kk] + (i & 3) * GST_BYTES + z, f[4 * kk], f[4 * kk + 1], f[4 * kk + 2], f[4 * kk + 3]);
          };
          const bool oddw = HALFW && (warp & 2);
          uint4 r0, r1;
          {
            const uint32_t t7 = HALFW ? (warp & 1) * 64 + (l >> 4) * 32 + (l & 15) : (warp & 3) * 32 + l;
            const uint32_t* pm = g_modp + wg * DM + ((cj * 128 + t7 * 4) & (DM - 1));
            const uint32_t* pr = g_ln1 + (rb * 128 + warp * 16 + (l >> 2)) * 4;
            uint4 m0 = make_uint4(tag, tag, tag, tag), m1 = m0;
            if (!oddw) { m0 = ld_relaxed4(pm); m1 = ld_relaxed4(pm + 2 * DM); }
            r0 = ld_b128(pr); r1 = ld_b128(pr + 32);
            fetch(0, a[0], 0); fetch(1, a[1], 0);
            uint32_t n = 0;
            bool written = false;
#pragma unroll 1
            while (true) {
              uint32_t miss;
              asm volatile("{ .reg .pred p0, p1, p2, p3; .reg .b32 t, u;\n"
                           "lop3.b32 t, %1, %2, %19, 0x7e; lop3.b32 u, %3, %4, %19, 0x7e; or.b32 t, t, u; and.b32 t, t, 3; setp.ne.u32 p0, t, 0;\n"
                           "lop3.b32 t, %5, %6, %19, 0x7e; lop3.b32 u, %7, %8, %19, 0x7e; or.b32 t, t, u; and.b32 t, t, 3; setp.ne.u32 p1, t, 0;\n"
                           "setp.ne.u32 p2, %12, %19; setp.ne.u32 p3, %16, %19;\n"
                           "@p0 ld.relaxed.gpu.global.v4.u32 {%1, %2, %3, %4}, [%17];\n"
                           "@p1 ld.relaxed.gpu.global.v4.u32 {%5, %6, %7, %8}, [%17 + 8192];\n"
                           "@p2 ld.relaxed.gpu.global.v4.u32 {%9, %10, %11, %12}, [%18];\n"
                           "@p3 ld.relaxed.gpu.global.v4.u32 {%13, %14, %15, %16}, [%18 + 128];\n"
                           "or.pred p0, p0, p1; or.pred p2, p2, p3; vote.sync.any.pred p0, p0, 0xffffffff; vote.sync.any.pred p2, p2, 0xffffffff;\n"
                           "selp.u32 t, 1, 0, p0; selp.u32 u, 2, 0, p2; or.b32 %0, t, u; }"
                           : "=r"(miss), "+r"(m0.x), "+r"(m0.y), "+r"(m0.z), "+r"(m0.w), "+r"(m1.x), "+r"(m1.y), "+r"(m1.z), "+r"(m1.w),
                             "+r"(r0.x), "+r"(r0.y), "+r"(r0.z), "+r"(r0.w), "+r"(r1.x), "+r"(r1.y), "+r"(r1.z), "+r"(r1.w)
                           : "l"(pm), "l"(pr), "r"(tag) : "memory");
              if (!(miss & 1) && !written) {
                written = true;
                if (!oddw) write_table(par, wg, t7, m0, m1);
                mbar_arrive(bar_mod);
              }
              if (!miss) break;
              watchdog(n);
            }
          }
          const uint32_t zero = r0.w ^ tag;
          auto normalize = [&](uint32_t (&f)[16]) {
#pragma unroll
            for (int k = 0; k < 16; k += 2) { f[k] = ln_norm(f[k], r0.x, r0.y, r0.z); f[k + 1] = ln_norm(f[k + 1], r1.x, r1.y, r1.z); }
          };
          auto modulate = [&](int i, uint32_t (&f)[16]) {
#pragma unroll
            for (int kk = 0; kk < 4; kk++) {
              const uint4 m = lds4(mt + slice_of(i) * 256 + kk * 64);
              f[4 * kk] = MODUL(f[4 * kk], m.x, m.z); f[4 * kk + 1] = MODUL(f[4 * kk + 1], m.x, m.z);
              f[4 * kk + 2] = MODUL(f[4 * kk + 2], m.y, m.w); f[4 * kk + 3] = MODUL(f[4 * kk + 3], m.y, m.w);
            }
            keep(f);
            mbar_arrive_pred(xempty + (i & 3) * 8, l == 0);
          };
          auto publish = [&](int u, uint32_t (&f)[16]) {
#pragma unroll
            for (int kk = 0; kk < 4; kk++) stmatrix4(fa[kk] + OFF_STAGE + u * UNIT, f[4 * kk], f[4 * kk + 1], f[4 * kk + 2], f[4 * kk + 3]);
            __syncwarp();
            mbar_arrive_pred(bar_hpub + u * 8, l == 0);
          };
          auto multiply = [&](int i, uint32_t (&f)[16]) {
            mbar_wait(gfull + (i & 3) * 8, i >> 2);
            const uint64_t db = make_desc(base + (i & 3) * GST_BYTES + UNIT, 8192, 1024);
            wg_fence();
#pragma unroll
            for (int kk = 0; kk < 4; kk++) mma256_rs(ga, gb, f[4 * kk], f[4 * kk + 1], f[4 * kk + 2], f[4 * kk + 3], db + kk * 128);
            wg_commit();
          };
          auto next = [&](int i, uint32_t (&f)[16]) {
            wg_wait<1>();
            mbar_arrive_cl(rempty, GE + ((i + 2) & 3) * 8);
            uint32_t z = zero;
#pragma unroll
            for (int k = 0; k < 16; k += 2) asm volatile("lop3.b32 %0, %1, %2, %0, 0xA8;" : "+r"(z) : "r"(f[k]), "r"(f[k + 1]));
            fetch(i, f, z);
            normalize(f); modulate(i, f); multiply(i, f);
          };
          normalize(a[0]); normalize(a[1]);
          keep(a[0]); keep(a[1]);
          mbar_wait(bar_mod, 0);
          PROF(1, tid == 0, 2);
          modulate(0, a[0]); multiply(0, a[0]); publish(0, a[0]);
          modulate(1, a[1]); multiply(1, a[1]);
          if (HALFW) mbar_wait(bar_mod2, 0); else publish(1, a[1]);
#pragma unroll 1
          for (int i = 2; i < NRS; i += 2) {
            next(i, a[0]);
            if (HALFW && i == 2) publish(1, a[0]);
            next(i + 1, a[1]);
          }
          wg_wait<1>();
          mbar_arrive_cl(rempty, GE + ((NRS + 2) & 3) * 8);
#pragma unroll 1
          for (int i = NRS; i < 14; i++) {
            mbar_wait(xfull + (i & 3) * 8, (i >> 2) & 1);
            mbar_wait(gfull + (i & 3) * 8, (i >> 2) & 1);
            const uint32_t xa = base + (i & 3) * GST_BYTES;
            const uint64_t da = make_desc(xa + wg * 8192, 16, 1024), db = make_desc(xa + UNIT, 8192, 1024);
            if (i == 13) bar_sync(2 + wg, 256);
            wg_fence();
#pragma unroll
            for (int kk = 0; kk < 4; kk++) mma256_ss(ga, gb, da + kk * 2, db + kk * 128, 1);
            wg_commit();
            if (i == 13) bar_arrive(3 - wg, 256);
            wg_wait<1>();
            uint32_t z = zero;
#pragma unroll
            for (int k = 0; k < 16; k += 2) asm volatile("lop3.b32 %0, %1, %2, %0, 0xA8;" : "+r"(z) : "r"(a[1][k]), "r"(a[1][k + 1]));
            mbar_arrive_cl(rempty, GE + ((i + 3) & 3) * 8 + z);
            mbar_arrive_pred(xempty + ((i + 3) & 3) * 8, l == 0 && i != NRS);
          }
          mbar_wait(xfull + 16, 1);
          wg_wait<0>();
          keep(ga); keep(gb);
#pragma unroll
          for (int i = 0; i < 64; i++) {
            asm volatile("mov.b32 %0, %1;" : "=f"(s[i]) : "f"(ga[i]));
            asm volatile("mov.b32 %0, %1;" : "=f"(o[i]) : "f"(gb[i]));
          }
        } else {
          float ga[64], gb[64];
#pragma unroll
          for (int i = 0; i < 64; i++) {
            asm volatile("mov.b32 %0, %1;" : "=f"(ga[i]) : "f"(s[i]));
            asm volatile("mov.b32 %0, %1;" : "=f"(gb[i]) : "f"(o[i]));
          }
#pragma unroll 1
          for (int i = 0; i < nst; i++) {
            mbar_wait(gfull + (i & 3) * 8, (i >> 2) & 1);
            const uint64_t da = make_desc(base + unit_of(xt, i & 3) + wg * 8192, 16, 1024), db = make_desc(base + unit_of(wt, i & 3), 8192, 1024);
            if (i == nst - 1) bar_sync(2 + wg, 256);
            wg_fence();
#pragma unroll
            for (int kk = 0; kk < 4; kk++) mma256_ss(ga, gb, da + kk * 2, db + kk * 128, kk ? 1 : i);
            wg_commit();
            if (i == nst - 1) bar_arrive(3 - wg, 256);
            wg_wait<1>();
            mbar_arrive_cl(rempty, GE + ((i + 3) & 3) * 8, i != 0);
            PROF(4, tid == 0 && (i & 3) == 0, 40 + (ps - 1) * 4 + i / 4);
          }
          wg_wait<0>();
          keep(ga); keep(gb);
#pragma unroll
          for (int i = 0; i < 64; i++) {
            asm volatile("mov.b32 %0, %1;" : "=f"(s[i]) : "f"(ga[i]));
            asm volatile("mov.b32 %0, %1;" : "=f"(o[i]) : "f"(gb[i]));
          }
        }
        mbar_arrive_cl(rempty, GE + (ps == 2 ? 24 : 8));
        if (ps == 2) break;
      }
      const uint32_t qw = base + wg * 8192, qt = QT >> (16 * ps), at = ps ? AT1 : AT0;
      {
        const uint32_t wt = ps ? WT1 : WT0;
        const uint64_t da0 = make_desc(qw + unit_of(qt, 2), 16, 1024), da1 = make_desc(qw + unit_of(qt, 3), 16, 1024);
        const uint64_t db0 = make_desc(base + unit_of(wt, 2), 8192, 1024), db1 = make_desc(base + unit_of(wt, 3), 8192, 1024);
        mbar_wait(gfull + 16, 1);
        bar_sync(2 + wg, 256);
        wg_fence();
#pragma unroll
        for (int kk = 0; kk < 4; kk++) mma_ss<1>(s, da0 + kk * 2, db0 + kk * 128, 1);
        wg_commit();
        mbar_wait(xfull + 24, 1);
        mbar_wait(gfull + 24, 1);
        wg_fence();
#pragma unroll
        for (int kk = 0; kk < 4; kk++) mma_ss<1>(s, da1 + kk * 2, db1 + kk * 128, 1);
        wg_commit();
        bar_arrive(3 - wg, 256);
        mbar_wait(ps == 0 ? bar_pread : bar_ofree + 8, 0);
        wg_wait<0>();
        keep(s);
        PROF(2, tid == 0, 8 + ps * 8);
        uint32_t q[32];
        pack_p(s, q);
#pragma unroll
        for (int i = 0; i < 4; i++) stmatrix4((qw + unit_of(qt, 0) + frag_offset(warp)) ^ (i << 5), q[4 * i], q[4 * i + 1], q[4 * i + 2], q[4 * i + 3]);
        keep(q);
        bar_sync(2 + wg, 256);
        wg_fence();
#pragma unroll
        for (int kk = 0; kk < 8; kk++) mma_ss<1>(o, (kk < 4 ? da0 : da1) + (kk & 3) * 2, (kk < 4 ? db0 : db1) + UNIT / 16 + (kk & 3) * 128, 1);
        wg_commit();
        mbar_wait(bfull, 0);
        wg_fence();
        const uint64_t dk = make_desc(base + unit_of(at, 0), 16, 1024);
#pragma unroll
        for (int kk = 0; kk < 8; kk++) mma_rs<0>(s, q[4 * kk], q[4 * kk + 1], q[4 * kk + 2], q[4 * kk + 3], dk + (kk >> 2) * 1024 + (kk & 3) * 2, kk != 0);
        wg_commit();
        bar_arrive(3 - wg, 256);
#pragma unroll
        for (int i = 4; i < 8; i++) stmatrix4((qw + unit_of(qt, 1) + frag_offset(warp)) ^ ((i & 3) << 5), q[4 * i], q[4 * i + 1], q[4 * i + 2], q[4 * i + 3]);
        wg_wait<1>();
        keep(o);
        mbar_arrive_cl(rempty, GE + 16);
        mbar_arrive_cl(rempty, GE + 24);
        store_chunk<0>(o, qw + unit_of(qt, 2) + frag_offset(warp));
        store_chunk<1>(o, qw + unit_of(qt, 3) + frag_offset(warp));
        wg_wait<0>();
        keep(s);
        mbar_arrive_cl(rempty, 0);
      }
      PROF(4, tid == 0 && ps == 1, 61);
      float l0 = 0.f, l1 = 0.f;
      auto step = [&](auto odd_c, const int j, uint32_t (&pw)[32], uint32_t (&pr)[32]) {
        constexpr bool ODD = decltype(odd_c)::value;
        const bool first = !ODD && (j & 2) == 0, last = ODD && j == 7;
        const uint32_t ph = (j >> 1) & 1;
        float i0, i1, a0, a1;
        const bool so = !ODD && j == 4;
        if (so) { i0 = inv_quad_sum(l0); i1 = inv_quad_sum(l1); l0 = 0.f; l1 = 0.f; }
        bool redo = !ODD && (j | ps) == 0;
        while (true) {
          if (redo) {
            float m0 = fmaxf(s[0], s[1]), m1 = fmaxf(s[2], s[3]);
#pragma unroll
            for (int i = 1; i < 16; i++) { m0 = fmaxf(m0, fmaxf(s[4 * i], s[4 * i + 1])); m1 = fmaxf(m1, fmaxf(s[4 * i + 2], s[4 * i + 3])); }
            m0 = fmaxf(m0, __shfl_xor_sync(0xffffffffu, m0, 1)); m1 = fmaxf(m1, __shfl_xor_sync(0xffffffffu, m1, 1));
            m0 = fmaxf(m0, __shfl_xor_sync(0xffffffffu, m0, 2)); m1 = fmaxf(m1, __shfl_xor_sync(0xffffffffu, m1, 2));
            m0 *= SCL2; m1 *= SCL2;
            if (!first) {
              m0 = fmaxf(m0, f0); m1 = fmaxf(m1, f1);
              const float c0 = ex2(f0 - m0), c1 = ex2(f1 - m1);
              l0 *= c0; l1 *= c1;
              wg_wait<0>();
              keep(o);
#pragma unroll
              for (int i = 0; i < 16; i++) { o[4 * i] *= c0; o[4 * i + 1] *= c0; o[4 * i + 2] *= c1; o[4 * i + 3] *= c1; }
            }
            f0 = m0; f1 = m1;
          }
          float b0 = 0.f, b1 = 0.f;
          a0 = 0.f; a1 = 0.f;
#pragma unroll
          for (int i = 0; i < 16; i++) {
            const float e0 = ex2(fmaf(s[4 * i], SCL2, -f0)), e1 = ex2(fmaf(s[4 * i + 1], SCL2, -f0));
            const float e2 = ex2(fmaf(s[4 * i + 2], SCL2, -f1)), e3 = ex2(fmaf(s[4 * i + 3], SCL2, -f1));
            a0 += e0; b0 += e1; a1 += e2; b1 += e3;
            pw[2 * i] = pack_bf(e0, e1); pw[2 * i + 1] = pack_bf(e2, e3);
            if (i == VREL) {
#pragma unroll
              for (int k = 0; k < 2 * VREL + 2; k++) asm volatile("" : "+r"(pw[k])::"memory");
              mbar_wait(bar_mod, 0);
              wg_wait<0>();
              mbar_arrive_cl(rempty, ODD ? 16 : 0, !redo && (ODD || j));
#pragma unroll
              for (int k = 4 * VREL + 4; k < 64; k++) asm volatile("" : "+f"(s[k])::"memory");
            }
          }
          a0 += b0; a1 += b1;
          if (redo) break;
          redo = __any_sync(0xffffffffu, !(a0 + a1 < 0x1p90f));
          if (first) {
            uint32_t m0 = __ballot_sync(0xffffffffu, a0 > 0x1p-80f), m1 = __ballot_sync(0xffffffffu, a1 > 0x1p-80f);
            m0 |= m0 >> 1; m1 |= m1 >> 1; m0 |= m0 >> 2; m1 |= m1 >> 2;
            redo = redo || (m0 & m1 & 0x11111111u) != 0x11111111u;
          }
          if (!redo) break;
        }
        l0 += a0; l1 += a1;
        keep(pw);
        keep(o);
        if (so) store_chunk<0>(o, i0, i1, qw + unit_of(qt, 0) + frag_offset(warp));
        keep(o);
        if (j == (ODD ? 5 : 0)) { fence_async_smem(); if (ODD) mbar_arrive(bar_ofull + wg * 8); }
        mbar_wait(bfull + (ODD ? 24 : 8), ph);
        bar_sync(2 + wg, 256);
        if (!last) {
          const uint32_t qn = qt >> (j >= 3 ? 8 : 0);
          wg_fence();
          issue_qk(s, qw + unit_of(qn, 0), qw + unit_of(qn, 1), base + unit_of(at, ODD ? 3 : 1));
          wg_commit();
          mbar_wait(bfull + (ODD ? 0 : 16), ODD ? ph ^ 1 : ph);
        }
        if (so) { store_chunk<1>(o, i0, i1, qw + unit_of(qt, 1) + frag_offset(warp)); keep(o); }
        wg_fence();
        issue_pv(o, pw, base + unit_of(at, ODD ? (last ? 3 : 0) : 2), !first);
        wg_commit();
        bar_arrive(3 - wg, 256);
        wg_wait<1>();
        keep(s);
        mbar_arrive_cl(rempty, ODD ? 24 : 8, !last);
        PROF(4, tid == 0 && ps == 1, 51 + j);
      };
      uint32_t pa[32], pb[32];
#pragma unroll 1
      for (int j = 0; j < 8; j += 2) {
        step(std::false_type{}, j, pa, pb);
        step(std::true_type{}, j + 1, pb, pa);
      }
      {
        const float i0 = inv_quad_sum(l0), i1 = inv_quad_sum(l1);
        wg_wait<0>();
        keep(o);
        mbar_arrive_cl(rempty, 24);
        store_chunk<0>(o, i0, i1, qw + unit_of(qt, 2) + frag_offset(warp));
        store_chunk<1>(o, i0, i1, qw + unit_of(qt, 3) + frag_offset(warp));
        fence_async_smem();
        mbar_arrive(bar_ofull + 16 + wg * 8);
      }
      PROF(2, tid == 0, 10 + ps * 8);
    }

    const int ln = fresh_lane(), g = ln >> 2, tq = ln & 3, ct = warp * 32 + ln;
    const bool lane0 = ln == 0;
    const int lrow0 = warp * 16 + g;
    const int grow0 = rb * 128 + lrow0;
    const uint32_t res = base + OFF_RES, trow = res + wg * 8192 + frag_offset(warp);
    uint32_t xr[32];
    uint4 sv[4], own;
    uint32_t* sp[4];
#pragma unroll
    for (int k = 0; k < 4; k++) sp[k] = g_stats + ((((tq >> 1) * 4 + k) ^ cj) * SEQ + grow0 + (tq & 1) * 8) * 4;
    {
      const uint64_t da = make_desc(base + wg * 8192, 16, 1024), db = make_desc(base, 8192, 1024);
      constexpr int U = UNIT / 16;
#define HALF_STAGE(acc, xu, wu) _Pragma("unroll") for (int kk = 0; kk < 4; kk++) mma_ss<1>(acc, da + (xu) * U + kk * 2, db + (wu) * U + kk * 128, 1)
      PROF(10, ct == PT, 19); STAMP(0);
      cluster_arrive();
      mbar_wait(gfull, 1);
      mbar_wait(gfull + 8, 1);
      bar_sync(2 + wg, 256);
      wg_fence();
      HALF_STAGE(o, 7, 1);
      HALF_STAGE(o, 8, 3);
      wg_commit();
      STAMP(16);
      mbar_wait(gfull + 16, 1);
      STAMP(17);
      wg_fence();
      HALF_STAGE(o, 6, 11);
      wg_commit();
      bar_arrive(3 - wg, 256);
      mbar_wait(bar_par, 0);
      uint32_t* xo = g_xch + ((size_t)b * 8 * 256 + ct) * 4;
      const uint32_t* xi = g_xch + ((size_t)(b ^ 2) * 8 * 256 + ct) * 4;
      const uint32_t par1 = (~lds1(par + PAR_CONST + 4) & 1) << 16;
      wg_wait<1>();
      mbar_arrive_pred(bar_rel, lane0);
      wg_wait<0>();
      keep(o);
      mbar_arrive_pred(bar_ring, lane0);
      PROF(8, ct == PT, 20); STAMP(1);
#define SEND(i) st_b128(xo + (i) * 1024, (pack_bf(o[8 * (i)], o[8 * (i) + 1]) & ~0x10000u) | par1, pack_bf(o[8 * (i) + 2], o[8 * (i) + 3]), \
                        pack_bf(o[8 * (i) + 4], o[8 * (i) + 5]), pack_bf(o[8 * (i) + 6], o[8 * (i) + 7]))
#pragma unroll
      for (int i = 0; i < NS1; i++) SEND(i);
      PROF(8, ct == PT, 21); STAMP(2);
      bar_sync(2 + wg, 256);
      wg_fence();
      HALF_STAGE(s, 7, 0);
      HALF_STAGE(s, 8, 2);
      HALF_STAGE(s, 6, 10);
      wg_commit();
      bar_arrive(3 - wg, 256);
      STAMP(18);
      mbar_wait(gfull + 24, 1);
#pragma unroll
      for (int i = NS1; i < 8; i++) SEND(i);
      uint4 v[8];
#pragma unroll
      for (int i = 0; i < LD1; i++) v[i] = ld_b128(xi + i * 1024);
      STAMP(19);
      mbar_wait(bar_xres, 0);
      wg_wait<0>();
      mbar_arrive_pred(bar_ring + 8, lane0);
      bar_sync(2 + wg, 256);
      STAMP(20);
#pragma unroll
      for (int i = LD1; i < LD2; i++) v[i] = ld_b128(xi + i * 1024);
      mbar_wait(bar_xres, 0);
      wg_fence();
      HALF_STAGE(s, 9, 4);
      wg_commit();
      mbar_wait(bar_rx, 0);
      wg_fence();
      HALF_STAGE(s, 1, 5);
      wg_commit();
      bar_arrive(3 - wg, 256);
      STAMP(21);
#pragma unroll
      for (int i = LD2; i < 8; i++) v[i] = ld_b128(xi + i * 1024);
      if (LD2 < 8) mbar_wait(bar_xres, 0);
      wg_wait<0>();
      keep(s);
      mbar_arrive_pred(bar_ring + 16, lane0);
      PROF(10, ct == PT, 23); STAMP(4);
#pragma unroll
      for (int i = 0; i < 16; i += 2) ldmatrix4((trow ^ ((i & 7) << 4)) + (i >> 3) * 16384, xr[2 * i], xr[2 * i + 1], xr[2 * i + 2], xr[2 * i + 3]);
      uint32_t ga[16];
      uint4 bw[8];
#pragma unroll
      for (int i = 0; i < 8; i++) {
        if (!(i & 1)) {
          const uint4 t = lds4(par + PAR_SINK + i * 32 + tq * 16);
          ga[2 * i] = t.x; ga[2 * i + 1] = t.y; ga[2 * i + 2] = t.z; ga[2 * i + 3] = t.w;
        }
        bw[i] = lds4(par + PAR_T1 + i * 64 + tq * 16);
        if (!(g & 1)) { bw[i].x = 0x3f803f80u; bw[i].y = 0x3f803f80u; }
      }
      uint32_t pk[32];
      pack_p(s, pk);
      keep(pk);
      {
        uint32_t n = 0, miss;
        do {
          miss = 0;
#pragma unroll
          for (int i = 0; i < 8; i++) miss |= v[i].x ^ par1;
          miss = __any_sync(0xffffffffu, miss & 0x10000u);
          if (miss) {
#pragma unroll
            for (int i = 0; i < 8; i++)
              asm volatile("{ .reg .pred p; .reg .b32 t; xor.b32 t, %0, %5; and.b32 t, t, 0x10000; setp.ne.u32 p, t, 0;\n"
                           "@p ld.relaxed.gpu.global.v4.u32 {%0, %1, %2, %3}, [%4]; }"
                           : "+r"(v[i].x), "+r"(v[i].y), "+r"(v[i].z), "+r"(v[i].w) : "l"(xi + i * 1024), "r"(par1) : "memory");
          }
          watchdog(n);
        } while (miss);
      }
      PROF(8, ct == PT, 22); STAMP(3);
      float ds[4] = {0.f, 0.f, 0.f, 0.f}, dl[4] = {0.f, 0.f, 0.f, 0.f}, q0[4] = {0.f, 0.f, 0.f, 0.f}, q1[4] = {0.f, 0.f, 0.f, 0.f};
#pragma unroll
      for (int i = 0; i < 8; i++) {
        const uint32_t u0 = hfma2(ga[2 * i], hadd2(pk[4 * i], v[i].x & ~0x10000u), xr[4 * i]);
        const uint32_t u1 = hfma2(ga[2 * i], hadd2(pk[4 * i + 1], v[i].y), xr[4 * i + 1]);
        const uint32_t u2 = hfma2(ga[2 * i + 1], hadd2(pk[4 * i + 2], v[i].z), xr[4 * i + 2]);
        const uint32_t u3 = hfma2(ga[2 * i + 1], hadd2(pk[4 * i + 3], v[i].w), xr[4 * i + 3]);
        xr[4 * i] = u0; xr[4 * i + 1] = u1; xr[4 * i + 2] = u2; xr[4 * i + 3] = u3;
        mma16816(ds, u0, u1, u2, u3, bw[i].x, bw[i].y);
        mma16816(dl, u0, u1, u2, u3, bw[i].z, bw[i].w);
        mma16816(q0, u0, u1, u2, u3, u0, u2);
        mma16816(q1, u0, u1, u2, u3, u1, u3);
      }
      const float sqa = __shfl_sync(0xffffffffu, (g & 1) ? q0[1] : q0[0], g * 4 + (g >> 1));
      const float sqb = __shfl_sync(0xffffffffu, (g & 1) ? q1[3] : q1[2], g * 4 + (g >> 1));
      own = (tq & 1) ? make_uint4(__float_as_uint(ds[2]), __float_as_uint(sqb), __float_as_uint(ds[3] + dl[3]), tag)
                                 : make_uint4(__float_as_uint(ds[0]), __float_as_uint(sqa), __float_as_uint(ds[1] + dl[1]), tag);
      if (tq < 2) st_b128(sp[0], own.x, own.y, own.z, own.w);
#pragma unroll
      for (int k = 0; k < 4; k++) sv[k] = make_uint4(0, 0, 0, 0);
    }
    PROF(8, ct == PT, 29); STAMP(5);
    uint32_t mm, ih, il;
    float rbest;
    uint32_t wf[128];
    const uint32_t frow = (ln & 7) + (ln >> 4) * 8;
    const uint32_t wfo = base + (warp & 1) * 8192 + frow * 64 + ((((ln >> 3) & 1) ^ ((frow >> 1) & 3)) << 4);
#define LOAD_WF(m) _Pragma("unroll") for (int f = 0; f < 16; f++) {                                                   \
      const int r = ((f >> 1) * 4 + (m) * 2 + (f & 1)) * 4;                                                           \
      ldmatrix4t(((wfo + unit_of((m) ? FT_U : FT_G, warp >> 1)) ^ ((f & 1) * 32)) + (f >> 1) * 1024, wf[r], wf[r + 1], wf[r + 2], wf[r + 3]); \
    }
    bool early;
    {
#pragma unroll
      for (int i = 0; i < 16; i += 2) stmatrix4((trow ^ ((i & 7) << 4)) + (i >> 3) * 16384, xr[2 * i], xr[2 * i + 1], xr[2 * i + 2], xr[2 * i + 3]);
      const uint4 cst = lds4(par + PAR_CONST);
      const float A1 = __uint_as_float(cst.x), A2 = __uint_as_float(cst.z);
      uint32_t n = 0;
      early = false;
#pragma unroll 1
      while (true) {
        uint32_t miss;
        asm volatile("{ .reg .pred p0, p1, p2, p3; .reg .b64 u, v; .reg .b128 w;\n"
                     "setp.ge.u32 p0, %22, 2; setp.ne.and.u32 p0, %4, %21, p0; setp.ne.u32 p1, %8, %21; setp.ne.u32 p2, %12, %21; setp.ne.u32 p3, %16, %21;\n"
                     "@p0 ld.relaxed.gpu.global.v4.u32 {%1, %2, %3, %4}, [%17];\n"
                     "@p1 ld.relaxed.gpu.global.v4.u32 {%5, %6, %7, %8}, [%18];\n"
                     "@p2 ld.relaxed.gpu.global.v4.u32 {%9, %10, %11, %12}, [%19];\n"
                     "@p3 ld.relaxed.gpu.global.v4.u32 {%13, %14, %15, %16}, [%20];\n"
                     "or.pred p0, p0, p1; or.pred p2, p2, p3; or.pred p0, p0, p2; vote.sync.any.pred p0, p0, 0xffffffff; selp.u32 %0, 1, 0, p0; }"
                     : "=r"(miss), "+r"(sv[0].x), "+r"(sv[0].y), "+r"(sv[0].z), "+r"(sv[0].w), "+r"(sv[1].x), "+r"(sv[1].y), "+r"(sv[1].z), "+r"(sv[1].w),
                       "+r"(sv[2].x), "+r"(sv[2].y), "+r"(sv[2].z), "+r"(sv[2].w), "+r"(sv[3].x), "+r"(sv[3].y), "+r"(sv[3].z), "+r"(sv[3].w)
                     : "l"(sp[0]), "l"(sp[1]), "l"(sp[2]), "l"(sp[3]), "r"(tag), "r"(tq) : "memory");
        if (!miss) break;
        if (!early && (b >= NFFN || __all_sync(0xffffffffu, mbar_test(bar_box + (warp >> 1) * 8, 0)))) {
          early = true;
          LOAD_WF(0);
          __syncwarp();
          mbar_arrive_pred(bar_gate, lane0);
        }
        watchdog(n);
      }
      const uint4 v0 = tq < 2 ? own : sv[0], v1 = sv[1], v2 = sv[2], v3 = sv[3];
      PROF(8, ct == PT, 30); STAMP(6);
      float su = (__uint_as_float(v0.x) + __uint_as_float(v1.x)) + (__uint_as_float(v2.x) + __uint_as_float(v3.x));
      float sq = (__uint_as_float(v0.y) + __uint_as_float(v1.y)) + (__uint_as_float(v2.y) + __uint_as_float(v3.y));
      float dt = (__uint_as_float(v0.z) + __uint_as_float(v1.z)) + (__uint_as_float(v2.z) + __uint_as_float(v3.z));
      su += __shfl_xor_sync(0xffffffffu, su, 2); sq += __shfl_xor_sync(0xffffffffu, sq, 2); dt += __shfl_xor_sync(0xffffffffu, dt, 2);
      const float m = su * (1.f / DM);
      float mb, sd;
      ln_scalars(m, fmaxf(sq * (1.f / DM) - m * m, 0.f), mb, sd);
      const float inv = rcp(sd);
      rbest = (dt - mb * A1) * inv + A2;
      mm = pack_bf(mb, mb);
      ih = pack_bf(inv, inv);
      const float lo = inv - bf_lo(ih);
      il = pack_bf(lo, lo);
    }
    int ibest;
    {
      const uint32_t bits = __float_as_uint(rbest);
      const uint32_t key = (((int)bits < 0 ? ~bits : bits | 0x80000000u) & ~0x1ffu) | ((127 - lrow0 - (tq & 1) * 8) << 2) | tag;
      sts1(par + PAR_RED + warp * 4, __reduce_max_sync(0xffffffffu, key));
      PROF(8, ct == PT, 38); STAMP(7);
      bar_sync(1, 256);
      const uint4 ka = lds4(par + PAR_RED), kb = lds4(par + PAR_RED + 16);
      const uint32_t k2 = max(max(max(ka.x, ka.y), max(ka.z, ka.w)), max(max(kb.x, kb.y), max(kb.z, kb.w)));
      if (ct == 0 && cj == 0) st_relaxed(g_cand + rb, k2);
      ibest = 127 - ((k2 >> 2) & 127);
    }
    PROF(8, ct == PT, 39); STAMP(8);
    if ((ibest >> 4) == warp) {
      const int src = (ibest & 7) * 4 + ((ibest >> 3) & 1), ch = g * 2;
      const uint32_t cm = __shfl_sync(0xffffffffu, mm, src), ch_ = __shfl_sync(0xffffffffu, ih, src), cl = __shfl_sync(0xffffffffu, il, src);
      const uint32_t xa = res + (ch >> 3) * 16384 + ibest * 128 + (((ch & 7) ^ (ibest & 7)) << 4) + tq * 4;
      const uint32_t x0 = lds1(xa), x1 = lds1(xa ^ 16);
      const uint2 p0 = lds2(par + PAR_T2 + ch * 64 + tq * 16), p1 = lds2(par + PAR_T2 + ch * 64 + 64 + tq * 16);
      uint32_t* dst = g_row + rb * 2 * DM + cj * 128 + ln * 4;
      st_pairs(dst, ln_mod(x0, cm, ch_, cl, p0.x, p0.y), ln_mod(x1, cm, ch_, cl, p1.x, p1.y), tag);
      st_pairs(dst + DM, x0, x1, tag);
      __syncwarp();
    }
    PROF(8, ct == PT, 37); STAMP(9);
    uint32_t wd[64];
    const uint32_t wda = base + unit_of(FT_D, warp >> 1) + (warp & 1) * 8192 + frow * 128 + ((((ln >> 3) & 1) ^ (ln & 7)) << 4);
#define LOAD_WD(f) ldmatrix4t((wda ^ ((((f) >> 1) & 3) * 32)) + ((f) >> 3) * 4096 + ((f) & 1) * 2048, wd[4 * (f)], wd[4 * (f) + 1], wd[4 * (f) + 2], wd[4 * (f) + 3])
    if (!early) {
      if (b < NFFN) mbar_wait(bar_box + (warp >> 1) * 8, 0);
      LOAD_WF(0);
      __syncwarp();
      mbar_arrive_pred(bar_gate, lane0);
    }
    if (b < NFFN) {
      const uint32_t own = base + unit_of(FT_G, warp >> 1) + (warp & 1) * 8192;
      mbar_wait(bar_box + (4 + (warp >> 1)) * 8, 0);
      LOAD_WF(1);
      uint32_t* const ydst = g_ypart + ((size_t)(warp * 16 + tq * 2) * NFFN + b) * 8 + g;
      PROF(8, ct == PT, 31); STAMP(10);
      bool wdok;
      {
        uint32_t n = 0;
        while (!(wdok = __all_sync(0xffffffffu, mbar_test(bar_box + (8 + (warp >> 1)) * 8, 0))) && !__all_sync(0xffffffffu, mbar_test(bar_sel, 0))) watchdog(n);
      }
      if (wdok) {
#pragma unroll
        for (int f = 0; f < 16; f++) LOAD_WD(f);
      }
      STAMP(11);
      mbar_wait(bar_sel, 0);
      PROF(8, ct == PT, 33); STAMP(12);
      float d[8][4];
#pragma unroll
      for (int i = 0; i < 4; i++) { d[i][0] = 0.f; d[i][1] = 0.f; d[i][2] = 0.f; d[i][3] = 0.f; }
#pragma unroll
      for (int ks = 0; ks < 8; ks++) {
        const uint2 hb = lds2(own + 256 + ks * 32 + tq * 8);
#pragma unroll
        for (int mt = 0; mt < 4; mt++) {
          const int r = ks * 16 + mt * 4;
          mma16816(d[mt], wf[r], wf[r + 1], wf[r + 2], wf[r + 3], hb.x, hb.y);
        }
      }
      sts2(own + (tq * 8 + g) * 8, __float_as_uint((tq & 2) ? ((tq & 1) ? d[1][2] : d[1][0]) : ((tq & 1) ? d[0][2] : d[0][0])),
           __float_as_uint((tq & 2) ? ((tq & 1) ? d[3][2] : d[3][0]) : ((tq & 1) ? d[2][2] : d[2][0])));
      bar_sync(1, 256);
      uint32_t ab[4];
      {
        float G = 0.f, U = 0.f;
        uint2 pv[8];
#pragma unroll
        for (int w8 = 0; w8 < 8; w8++) pv[w8] = lds2(base + ln * 8 + ((FT_G >> (w8 >> 1) * 4) & 15) * UNIT + (w8 & 1) * 8192);
#pragma unroll
        for (int w8 = 0; w8 < 8; w8 += 2) {
          G += __uint_as_float(pv[w8].x) + __uint_as_float(pv[w8 + 1].x);
          U += __uint_as_float(pv[w8].y) + __uint_as_float(pv[w8 + 1].y);
        }
        const float act = rbf(silu_f(rbf(G))) * rbf(U);
        const uint32_t pk = pack_bf(act, __shfl_down_sync(0xffffffffu, act, 1));
#pragma unroll
        for (int i = 0; i < 4; i++) ab[i] = __shfl_sync(0xffffffffu, pk, i * 8 + tq * 2);
      }
      if (!wdok) {
        mbar_wait(bar_box + (8 + (warp >> 1)) * 8, 0);
#pragma unroll
        for (int f = 0; f < 16; f++) LOAD_WD(f);
      }
      PROF(8, ct == PT, 34); STAMP(13);
#pragma unroll
      for (int mt = 0; mt < 8; mt++) {
        d[mt][0] = 0.f; d[mt][1] = 0.f; d[mt][2] = 0.f; d[mt][3] = 0.f;
        mma16816(d[mt], wd[mt * 8], wd[mt * 8 + 1], wd[mt * 8 + 2], wd[mt * 8 + 3], ab[0], ab[1]);
        mma16816(d[mt], wd[mt * 8 + 4], wd[mt * 8 + 5], wd[mt * 8 + 6], wd[mt * 8 + 7], ab[2], ab[3]);
      }
#pragma unroll
      for (int i = 0; i < 4; i++) {
        const int m4 = (i >> 1) * 4, e = (i & 1) * 2;
        const float y = (tq & 2) ? ((tq & 1) ? d[m4 + 3][e] : d[m4 + 2][e]) : ((tq & 1) ? d[m4 + 1][e] : d[m4][e]);
        st_relaxed(ydst + (m4 * 2 + (i & 1)) * NFFN * 8, tagf(y, tag));
      }
      PROF(8, ct == PT, 35); STAMP(14);
    }
    mbar_wait(bar_sel, 0);
    mbar_arrive_pred(bar_win, ct == 0);
    const int iwin = lds1(par + PAR_CONST + 60) & 0x7ff;
    const bool cand = (iwin >> 4) == rb * 8 + warp;
    {
      const uint32_t mm0 = __shfl_sync(0xffffffffu, mm, ln & ~1), mm1 = __shfl_sync(0xffffffffu, mm, ln | 1);
      const uint32_t ih0 = __shfl_sync(0xffffffffu, ih, ln & ~1), ih1 = __shfl_sync(0xffffffffu, ih, ln | 1);
      const uint32_t il0 = __shfl_sync(0xffffffffu, il, ln & ~1), il1 = __shfl_sync(0xffffffffu, il, ln | 1);
#pragma unroll 1
      for (int hf = 0; hf < 2; hf++) {
        uint32_t x[16];
#pragma unroll
        for (int i = 0; i < 8; i += 2) ldmatrix4((trow ^ (i << 4)) + hf * 16384, x[2 * i], x[2 * i + 1], x[2 * i + 2], x[2 * i + 3]);
#pragma unroll
        for (int i = 0; i < 8; i++) {
          const uint4 pv = lds4(par + PAR_T2 + (hf * 8 + i) * 64 + tq * 16);
          x[2 * i] = hadd2(x[2 * i], hmul2(pv.z, ln_mod(x[2 * i], mm0, ih0, il0, pv.x, pv.y)));
          x[2 * i + 1] = hadd2(x[2 * i + 1], hmul2(pv.z, ln_mod(x[2 * i + 1], mm1, ih1, il1, pv.x, pv.y)));
        }
#pragma unroll
        for (int i = 0; i < 8; i += 2) stmatrix4((trow ^ (i << 4)) + hf * 16384, x[2 * i], x[2 * i + 1], x[2 * i + 2], x[2 * i + 3]);
      }
      if (!cand) fence_async_smem();
      __syncwarp();
      if (!cand && elect_one()) {
        tma2d_store(&maps.out, res + warp * 2048, cj * 128, rb * 128 + warp * 16);
        tma2d_store(&maps.out, res + 16384 + warp * 2048, cj * 128 + 64, rb * 128 + warp * 16);
        asm volatile("cp.async.bulk.commit_group;" ::: "memory");
      }
    }
    if (cand) {
      const int wrow0 = warp * 16;
#pragma unroll 2
      for (int p = 0; p < 8; p++) {
        const int row = 2 * p + (ln >> 4), ch = ln & 15;
        const uint4 v = lds4(res + (ch >> 3) * 16384 + (wrow0 + row) * 128 + (((ch & 7) ^ (row & 7)) << 4));
        if (rb * 128 + wrow0 + row != iwin) *reinterpret_cast<uint4*>(P.out + (size_t)(rb * 128 + wrow0 + row) * DM + cj * 128 + ch * 8) = v;
      }
    }
    asm volatile("cp.async.bulk.wait_group.read 0;" ::: "memory");
    PROF(8, ct == PT, 11); STAMP(15);
    cluster_wait();
  }
}

typedef CUresult (*EncodeFn)(CUtensorMap*, CUtensorMapDataType, cuuint32_t, void*, const cuuint64_t*, const cuuint64_t*,
                             const cuuint32_t*, const cuuint32_t*, CUtensorMapInterleave, CUtensorMapSwizzle,
                             CUtensorMapL2promotion, CUtensorMapFloatOOBfill);

void map2d(EncodeFn enc, CUtensorMap* m, const void* p, uint64_t rows, uint64_t cols, uint32_t brows) {
  cuuint64_t dims[2] = {cols, rows}, strides[1] = {cols * 2};
  cuuint32_t box[2] = {64, brows}, es[2] = {1, 1};
  enc(m, CU_TENSOR_MAP_DATA_TYPE_BFLOAT16, 2, const_cast<void*>(p), dims, strides, box, es, CU_TENSOR_MAP_INTERLEAVE_NONE,
      CU_TENSOR_MAP_SWIZZLE_128B, CU_TENSOR_MAP_L2_PROMOTION_L2_256B, CU_TENSOR_MAP_FLOAT_OOB_FILL_NONE);
}
void map2d_narrow(EncodeFn enc, CUtensorMap* m, const void* p, uint64_t rows, uint64_t cols, uint32_t brows) {
  cuuint64_t dims[2] = {cols, rows}, strides[1] = {cols * 2};
  cuuint32_t box[2] = {32, brows}, es[2] = {1, 1};
  enc(m, CU_TENSOR_MAP_DATA_TYPE_BFLOAT16, 2, const_cast<void*>(p), dims, strides, box, es, CU_TENSOR_MAP_INTERLEAVE_NONE,
      CU_TENSOR_MAP_SWIZZLE_64B, CU_TENSOR_MAP_L2_PROMOTION_L2_64B, CU_TENSOR_MAP_FLOAT_OOB_FILL_NONE);
}
void map3d(EncodeFn enc, CUtensorMap* m, const void* p, uint64_t rows, uint64_t cols, uint32_t brows, uint32_t nch) {
  cuuint64_t dims[3] = {64, rows, cols / 64}, strides[2] = {cols * 2, 128};
  cuuint32_t box[3] = {64, brows, nch}, es[3] = {1, 1, 1};
  enc(m, CU_TENSOR_MAP_DATA_TYPE_BFLOAT16, 3, const_cast<void*>(p), dims, strides, box, es, CU_TENSOR_MAP_INTERLEAVE_NONE,
      CU_TENSOR_MAP_SWIZZLE_128B, CU_TENSOR_MAP_L2_PROMOTION_L2_256B, CU_TENSOR_MAP_FLOAT_OOB_FILL_NONE);
}

}

extern "C" void kernel_launch(void* const* d_in, const int* in_sizes, int n_in, void* d_out, int out_size) {
  (void)in_sizes; (void)n_in; (void)out_size;
  static EncodeFn enc = nullptr;
  if (!enc) {
    void* fn = nullptr;
    cudaDriverEntryPointQueryResult st;
    cudaGetDriverEntryPoint("cuTensorMapEncodeTiled", &fn, cudaEnableDefault, &st);
    enc = (EncodeFn)fn;
    cudaFuncSetAttribute(fused_kernel, cudaFuncAttributeMaxDynamicSharedMemorySize, SMEM_BYTES);
  }
  Maps maps;
  map2d(enc, &maps.x, d_in[0], SEQ, DM, 128);
  map2d(enc, &maps.out, d_out, SEQ, DM, 16);
  map3d(enc, &maps.wq, d_in[3], DM, NQ, 64, 2);
  map3d(enc, &maps.k, d_in[1], 4 * SK, 128, 128, 1);
  map3d(enc, &maps.v, d_in[2], 4 * SK, 128, 128, 1);
  map3d(enc, &maps.wo, d_in[4], NQ, DM, 64, 2);
  map2d_narrow(enc, &maps.wg, d_in[7], DM, FF, 256);
  map2d_narrow(enc, &maps.wu, d_in[8], DM, FF, 256);
  map3d(enc, &maps.wd, d_in[9], FF, DM, 32, 4);
  map2d_narrow(enc, &maps.wm, d_in[11], DM, NMOD, 256);
  Ptrs p;
  p.x = (const __nv_bfloat16*)d_in[0];
  p.w_r = (const __nv_bfloat16*)d_in[6];
  p.w_gate = (const __nv_bfloat16*)d_in[7];
  p.w_up = (const __nv_bfloat16*)d_in[8];
  p.w_down = (const __nv_bfloat16*)d_in[9];
  p.c = (const __nv_bfloat16*)d_in[10];
  p.w_mod = (const __nv_bfloat16*)d_in[11];
  p.out = (__nv_bfloat16*)d_out;
  fused_kernel<<<NMAIN + NHELP, 384, SMEM_BYTES>>>(maps, p);
}
```

```cpp
#include <cuda_runtime.h>
#include <cuda_bf16.h>
#include <cuda.h>
#include <stdint.h>
#include <type_traits>

#define HD 2
#define HDX 2
#define NRS 8
#define FPACE 3
#define GOST 20
#define WB 2
#define WN 20
#define RES0 17
#define RES1 20
#define HU 32
#define NS1 5
#define PG0 15
#define PSL 0
#define FB0 0
#define FB2 8
#define OPS 8192
#define OFL 0
#define ODS 8
#define MODUL hfma2
#define ODS1 5
#define LD1 0
#define LD2 4
#define FB1 2
#define FPB 8
#define FPACE0 2
#define HWB 0
#define M2L 1
#define VREL 5
#define E0 3

namespace {

constexpr int SEQ = 2048, DM = 1024, NQ = 4096, SK = 2048, WIN = 512, FF = 3584, NMOD = 6144;
constexpr int NMAIN = 128, NHELP = 4, NFFN = 112;
constexpr int NSLOT = 4, SLOT_BYTES = 32768, UNIT = 16384, GST_BYTES = 3 * UNIT;
constexpr uint32_t XT1 = 0xDCBA, XT2 = 0x9687;
constexpr uint32_t WT0 = 0xA741, WT1 = 0x7420, WT2 = 0x4A20;
constexpr uint32_t AT0 = WT1, AT1 = WT2;
constexpr uint32_t QT = 0xDC9696DC;
constexpr int OFF_STAGE = 12 * UNIT;
constexpr uint32_t FT_G = 0x07B3, FT_U = 0xA628, FT_D = 0x5149;
constexpr int OFF_RES = 12 * UNIT;
constexpr int OFF_PAR = 14 * UNIT;
constexpr int OFF_BAR = OFF_PAR + 2528;
constexpr int SMEM_BYTES = OFF_BAR + 544;
static_assert(SMEM_BYTES <= 232448, "smem");

constexpr int PAR_T1 = 0;
constexpr int PAR_T2 = 512;
constexpr int PAR_CONST = 1536;
constexpr int PAR_RED = 1600;
constexpr int PAR_SINK = 2176;

struct Maps {
  CUtensorMap x, wq, k, v, wo, wg, wu, wd, wm, out;
};
struct Ptrs {
  const __nv_bfloat16 *x, *w_r, *c, *w_mod, *w_gate, *w_up, *w_down;
  __nv_bfloat16* out;
};

__device__ __align__(1024) uint8_t g_act[16 * 80 * UNIT];
__device__ __align__(128) uint32_t g_mod[NMOD];
__device__ __align__(128) uint32_t g_modp[2 * 2 * DM];
__device__ __align__(128) uint32_t g_ln1[SEQ * 4];
__device__ __align__(128) uint32_t g_cnt_h[16 * 32];
__device__ __align__(128) uint32_t g_cnt_o[128 * 32];
__device__ __align__(128) uint32_t g_xch[NMAIN * 8 * 256 * 4];
__device__ __align__(128) uint32_t g_stats[8 * SEQ * 4];
__device__ __align__(128) uint32_t g_cand[32];
__device__ __align__(128) uint32_t g_row[16 * 2 * DM];
__device__ __align__(128) uint32_t g_ypart[NMAIN * NFFN * 8];
__device__ uint32_t g_epoch;

__device__ __forceinline__ uint32_t fresh_lane() { uint32_t l; asm volatile("mov.u32 %0, %%laneid;" : "=r"(l)); return l; }
__device__ __forceinline__ uint32_t frag_offset(int warp) {
  const uint32_t l = fresh_lane();
  return ((warp & 3) * 16 + (l & 15)) * 128 + (((l >> 4) ^ (l & 7)) << 4);
}
__device__ __forceinline__ bool elect_one() {
  uint32_t p;
  asm volatile("{ .reg .pred q; elect.sync _|q, 0xffffffff; selp.u32 %0, 1, 0, q; }" : "=r"(p));
  return p;
}
__device__ __forceinline__ uint32_t smem_u32(const void* p) { return (uint32_t)__cvta_generic_to_shared(p); }
__device__ __forceinline__ void mbar_init(uint32_t bar, uint32_t cnt) {
  asm volatile("mbarrier.init.shared::cta.b64 [%0], %1;" ::"r"(bar), "r"(cnt) : "memory");
}
__device__ __forceinline__ void mbar_expect_tx(uint32_t bar, uint32_t bytes) {
  asm volatile("mbarrier.arrive.expect_tx.shared::cta.b64 _, [%0], %1;" ::"r"(bar), "r"(bytes) : "memory");
}
__device__ __forceinline__ void mbar_arrive(uint32_t bar) {
  asm volatile("mbarrier.arrive.shared::cta.b64 _, [%0];" ::"r"(bar) : "memory");
}
__device__ __forceinline__ void mbar_arrive_pred(uint32_t bar, bool p) {
  asm volatile("{ .reg .pred p; setp.ne.b32 p, %1, 0; @p mbarrier.arrive.shared::cta.b64 _, [%0]; }" ::"r"(bar), "r"((int)p) : "memory");
}
__device__ __forceinline__ void mbar_arrive_cl(uint32_t bar, uint32_t off, bool p = true) {
  asm volatile("{ .reg .pred p, q; .reg .b32 a; setp.ne.b32 q, %2, 0; setp.ne.and.b32 p, %0, 0, q; add.u32 a, %0, %1; @p mbarrier.arrive.shared::cluster.b64 _, [a]; }"
               ::"r"(bar), "r"(off), "r"((int)p) : "memory");
}
__device__ __forceinline__ uint32_t mapa(uint32_t addr, uint32_t cta) {
  uint32_t r; asm("mapa.shared::cluster.u32 %0, %1, %2;" : "=r"(r) : "r"(addr), "r"(cta)); return r;
}
__device__ __forceinline__ void cluster_arrive() { asm volatile("barrier.cluster.arrive.relaxed.aligned;" ::: "memory"); }
__device__ __forceinline__ void cluster_wait() { asm volatile("barrier.cluster.wait.aligned;" ::: "memory"); }
__device__ __forceinline__ void watchdog(uint32_t& n) {
}
__device__ __forceinline__ void mbar_wait(uint32_t bar, uint32_t parity) {
  asm volatile("{\n.reg .pred p;\nWAIT_%=:\nmbarrier.try_wait.parity.shared::cta.b64 p, [%0], %1;\n@!p bra WAIT_%=;\n}" ::"r"(bar), "r"(parity) : "memory");
}
__device__ __forceinline__ bool mbar_test(uint32_t bar, uint32_t parity) {
  uint32_t ok;
  asm volatile("{\n.reg .pred p;\nmbarrier.test_wait.parity.shared::cta.b64 p, [%1], %2;\nselp.u32 %0, 1, 0, p;\n}" : "=r"(ok) : "r"(bar), "r"(parity) : "memory");
  return ok;
}
__device__ __forceinline__ uint64_t l2_stream() {
  uint64_t f; asm("createpolicy.fractional.L2::evict_first.b64 %0, 1.0;" : "=l"(f)); return f;
}
__device__ __forceinline__ void tma2d(uint32_t dst, const CUtensorMap* m, int c0, int c1, uint32_t bar) {
  asm volatile("cp.async.bulk.tensor.2d.shared::cluster.global.mbarrier::complete_tx::bytes.L2::cache_hint [%0], [%1, {%3, %4}], [%2], %5;"
               ::"r"(dst), "l"(m), "r"(bar), "r"(c0), "r"(c1), "l"(l2_stream()) : "memory");
}
__device__ __forceinline__ void bulk_load(uint32_t dst, const void* src, uint32_t bytes, uint32_t bar) {
  asm volatile("cp.async.bulk.shared::cluster.global.mbarrier::complete_tx::bytes [%0], [%1], %2, [%3];" ::"r"(dst), "l"(src), "r"(bytes), "r"(bar) : "memory");
}
__device__ __forceinline__ void bulk_load_stream(uint32_t dst, const void* src, uint32_t bytes, uint32_t bar) {
  asm volatile("cp.async.bulk.shared::cluster.global.mbarrier::complete_tx::bytes.L2::cache_hint [%0], [%1], %2, [%3], %4;"
               ::"r"(dst), "l"(src), "r"(bytes), "r"(bar), "l"(l2_stream()) : "memory");
}
__device__ __forceinline__ void tma2d_store(const CUtensorMap* m, uint32_t src, int c0, int c1) {
  asm volatile("cp.async.bulk.tensor.2d.global.shared::cta.bulk_group [%0, {%2, %3}], [%1];" ::"l"(m), "r"(src), "r"(c0), "r"(c1) : "memory");
}
__device__ __forceinline__ void bulk_store(void* dst, uint32_t src, uint32_t bytes) {
  asm volatile("cp.async.bulk.global.shared::cta.bulk_group [%0], [%1], %2;" ::"l"(dst), "r"(src), "r"(bytes) : "memory");
}
__device__ __forceinline__ int slice_of(int i) { return i + ((i & 7) == 1) - ((i & 7) == 2); }
__device__ __forceinline__ uint32_t unit_of(uint32_t table, uint32_t i) { return ((table >> (i * 4)) & 15) * UNIT; }
__device__ __forceinline__ void tma3d(uint32_t dst, const CUtensorMap* m, int c0, int c1, int c2, uint32_t bar) {
  asm volatile("cp.async.bulk.tensor.3d.shared::cluster.global.mbarrier::complete_tx::bytes.L2::cache_hint [%0], [%1, {%3, %4, %5}], [%2], %6;"
               ::"r"(dst), "l"(m), "r"(bar), "r"(c0), "r"(c1), "r"(c2), "l"(l2_stream()) : "memory");
}
template <bool STREAM>
__device__ __forceinline__ void tma3d_mc(uint32_t dst, const CUtensorMap* m, int c0, int c1, int c2, uint32_t bar) {
  if (STREAM)
    asm volatile("cp.async.bulk.tensor.3d.shared::cluster.global.mbarrier::complete_tx::bytes.multicast::cluster.L2::cache_hint [%0], [%1, {%3, %4, %5}], [%2], %6, %7;"
                 ::"r"(dst), "l"(m), "r"(bar), "r"(c0), "r"(c1), "r"(c2), "h"((uint16_t)3), "l"(l2_stream()) : "memory");
  else
    asm volatile("cp.async.bulk.tensor.3d.shared::cluster.global.mbarrier::complete_tx::bytes.multicast::cluster [%0], [%1, {%3, %4, %5}], [%2], %6;"
                 ::"r"(dst), "l"(m), "r"(bar), "r"(c0), "r"(c1), "r"(c2), "h"((uint16_t)3) : "memory");
}
__device__ __forceinline__ void prefetch_map(const CUtensorMap* m) {
  asm volatile("prefetch.tensormap [%0];" ::"l"(m) : "memory");
}
__device__ __forceinline__ void fence_async() { asm volatile("fence.proxy.async.global;" ::: "memory"); }
__device__ __forceinline__ void fence_async_smem() { asm volatile("fence.proxy.async.shared::cta;" ::: "memory"); }
__device__ __forceinline__ void bar_sync(int id, int n) { asm volatile("bar.sync %0, %1;" ::"r"(id), "r"(n) : "memory"); }
__device__ __forceinline__ void bar_arrive(int id, int n) { asm volatile("bar.arrive %0, %1;" ::"r"(id), "r"(n) : "memory"); }
__device__ __forceinline__ void wg_fence() { asm volatile("wgmma.fence.sync.aligned;" ::: "memory"); }
__device__ __forceinline__ void wg_commit() { asm volatile("wgmma.commit_group.sync.aligned;" ::: "memory"); }
template <int N> __device__ __forceinline__ void wg_wait() { asm volatile("wgmma.wait_group.sync.aligned %0;" ::"n"(N) : "memory"); }
__device__ __forceinline__ uint64_t make_desc(uint32_t addr, uint32_t lbo, uint32_t sbo) {
  return (uint64_t)((addr & 0x3FFFF) >> 4) | ((uint64_t)(lbo >> 4) << 16) | ((uint64_t)(sbo >> 4) << 32) | (1ull << 62);
}
__device__ __forceinline__ uint32_t ld_relaxed(const uint32_t* p) {
  uint32_t v; asm volatile("ld.relaxed.gpu.global.u32 %0, [%1];" : "=r"(v) : "l"(p) : "memory"); return v;
}
__device__ __forceinline__ uint32_t ld_acquire(const uint32_t* p) {
  uint32_t v; asm volatile("ld.acquire.gpu.global.u32 %0, [%1];" : "=r"(v) : "l"(p) : "memory"); return v;
}
__device__ __forceinline__ uint4 ld_relaxed4(const uint32_t* p) {
  uint4 v; asm volatile("ld.relaxed.gpu.global.v4.u32 {%0,%1,%2,%3}, [%4];" : "=r"(v.x), "=r"(v.y), "=r"(v.z), "=r"(v.w) : "l"(p) : "memory"); return v;
}
__device__ __forceinline__ uint2 ld_relaxed2(const uint32_t* p) {
  uint2 v; asm volatile("ld.relaxed.gpu.global.v2.u32 {%0,%1}, [%2];" : "=r"(v.x), "=r"(v.y) : "l"(p) : "memory"); return v;
}
__device__ __forceinline__ void st_relaxed(uint32_t* p, uint32_t v) {
  asm volatile("st.relaxed.gpu.global.u32 [%0], %1;" ::"l"(p), "r"(v) : "memory");
}
__device__ __forceinline__ void st_relaxed2(uint32_t* p, uint32_t a, uint32_t b) {
  asm volatile("st.relaxed.gpu.global.v2.u32 [%0], {%1,%2};" ::"l"(p), "r"(a), "r"(b) : "memory");
}
__device__ __forceinline__ void st_relaxed4(uint32_t* p, uint32_t a, uint32_t b, uint32_t c, uint32_t d) {
  asm volatile("st.relaxed.gpu.global.v4.u32 [%0], {%1,%2,%3,%4};" ::"l"(p), "r"(a), "r"(b), "r"(c), "r"(d) : "memory");
}
__device__ __forceinline__ void st_b128(uint32_t* p, uint32_t a, uint32_t b, uint32_t c, uint32_t d) {
  asm volatile("{ .reg .b64 u, v; .reg .b128 w; mov.b64 u, {%1, %2}; mov.b64 v, {%3, %4}; mov.b128 w, {u, v}; st.relaxed.gpu.global.b128 [%0], w; }"
               ::"l"(p), "r"(a), "r"(b), "r"(c), "r"(d) : "memory");
}
__device__ __forceinline__ uint4 ld_b128(const uint32_t* p) {
  uint4 r;
  asm volatile("{ .reg .b64 u, v; .reg .b128 w; ld.relaxed.gpu.global.b128 w, [%4]; mov.b128 {u, v}, w; mov.b64 {%0, %1}, u; mov.b64 {%2, %3}, v; }"
               : "=r"(r.x), "=r"(r.y), "=r"(r.z), "=r"(r.w) : "l"(p) : "memory");
  return r;
}
__device__ __forceinline__ void st_pairs(uint32_t* p, uint32_t a, uint32_t b, uint32_t tag) {
  asm volatile("{ .reg .b64 u, v; mov.b64 u, {%1, %3}; mov.b64 v, {%2, %3}; st.relaxed.gpu.global.v2.b64 [%0], {u, v}; }"
               ::"l"(p), "r"(a), "r"(b), "r"(tag) : "memory");
}
__device__ __forceinline__ uint4 ld_pairs(const uint32_t* p) {
  uint4 v;
  asm volatile("{ .reg .b64 u, v; ld.relaxed.gpu.global.v2.b64 {u, v}, [%4]; mov.b64 {%0, %1}, u; mov.b64 {%2, %3}, v; }"
               : "=r"(v.x), "=r"(v.y), "=r"(v.z), "=r"(v.w) : "l"(p) : "memory");
  return v;
}
__device__ __forceinline__ uint2 ld_pair(const uint32_t* p) {
  uint2 v;
  asm volatile("{ .reg .b64 u; ld.relaxed.gpu.global.b64 u, [%2]; mov.b64 {%0, %1}, u; }" : "=r"(v.x), "=r"(v.y) : "l"(p) : "memory");
  return v;
}
__device__ __forceinline__ void red_release(uint32_t* p, uint32_t v) {
  asm volatile("red.release.gpu.global.add.u32 [%0], %1;" ::"l"(p), "r"(v) : "memory");
}
__device__ __forceinline__ uint32_t ldg_nc1(const void* p) {
  uint32_t v;
  asm volatile("ld.global.nc.u32 %0, [%1];" : "=r"(v) : "l"(p));
  return v;
}
__device__ __forceinline__ uint4 ldg_nc4(const void* p) {
  uint4 v; asm volatile("ld.global.nc.L1::no_allocate.v4.u32 {%0,%1,%2,%3}, [%4];" : "=r"(v.x), "=r"(v.y), "=r"(v.z), "=r"(v.w) : "l"(p)); return v;
}
__device__ __forceinline__ uint4 ldg_stream4(const void* p) {
  uint4 v;
  asm volatile("ld.global.nc.L1::no_allocate.L2::cache_hint.v4.u32 {%0,%1,%2,%3}, [%4], %5;" : "=r"(v.x), "=r"(v.y), "=r"(v.z), "=r"(v.w) : "l"(p), "l"(l2_stream()));
  return v;
}
__device__ __forceinline__ void stg4(void* p, uint4 v) {
  asm volatile("st.global.v4.u32 [%0], {%1,%2,%3,%4};" ::"l"(p), "r"(v.x), "r"(v.y), "r"(v.z), "r"(v.w) : "memory");
}
__device__ __forceinline__ void wait_counter(const uint32_t* p, uint32_t target) {
  uint32_t n = 0;
  while (__any_sync(0xffffffffu, (int)(ld_acquire(p) - target) < 0)) { watchdog(n); }
}
__device__ __forceinline__ uint32_t tagf(float v, uint32_t tag) { return (__float_as_uint(v) & ~3u) | tag; }
__device__ __forceinline__ bool tag_ok(uint4 v, uint32_t tag) { return (((v.x ^ tag) | (v.y ^ tag) | (v.z ^ tag) | (v.w ^ tag)) & 3u) == 0; }
__device__ __forceinline__ float untag_sum(uint32_t a, uint32_t b) { return __uint_as_float(a & ~3u) + __uint_as_float(b & ~3u); }
__device__ __forceinline__ uint4 poll4(const uint32_t* p, uint32_t tag) {
  uint4 v = ld_relaxed4(p);
  uint32_t n = 0;
  while (!__all_sync(0xffffffffu, tag_ok(v, tag))) { v = ld_relaxed4(p); watchdog(n); }
  return v;
}
__device__ __forceinline__ float bf_lo(uint32_t v) { return __uint_as_float(v << 16); }
__device__ __forceinline__ float bf_hi(uint32_t v) { return __uint_as_float(v & 0xffff0000u); }
__device__ __forceinline__ uint32_t pack_bf(float lo, float hi) {
  uint32_t r; asm("cvt.rn.bf16x2.f32 %0, %1, %2;" : "=r"(r) : "f"(hi), "f"(lo)); return r;
}
__device__ __forceinline__ float rbf(float v) { return __uint_as_float(pack_bf(0.f, v) & 0xffff0000u); }
__device__ __forceinline__ uint32_t hmul2(uint32_t a, uint32_t b) {
  uint32_t r; asm("mul.rn.bf16x2 %0, %1, %2;" : "=r"(r) : "r"(a), "r"(b)); return r;
}
__device__ __forceinline__ uint32_t hadd2(uint32_t a, uint32_t b) {
  uint32_t r; asm("add.rn.bf16x2 %0, %1, %2;" : "=r"(r) : "r"(a), "r"(b)); return r;
}
__device__ __forceinline__ uint32_t hsub2(uint32_t a, uint32_t b) {
  uint32_t r; asm("sub.rn.bf16x2 %0, %1, %2;" : "=r"(r) : "r"(a), "r"(b)); return r;
}
__device__ __forceinline__ uint32_t hmax2(uint32_t a, uint32_t b) {
  uint32_t r; asm("max.bf16x2 %0, %1, %2;" : "=r"(r) : "r"(a), "r"(b)); return r;
}
__device__ __forceinline__ float rcp(float x) { float r; asm("rcp.approx.ftz.f32 %0, %1;" : "=f"(r) : "f"(x)); return r; }
__device__ __forceinline__ float ex2(float x) { float r; asm("ex2.approx.ftz.f32 %0, %1;" : "=f"(r) : "f"(x)); return r; }
__device__ __forceinline__ void stmatrix4(uint32_t addr, uint32_t a, uint32_t b, uint32_t c, uint32_t d) {
  asm volatile("stmatrix.sync.aligned.m8n8.x4.shared.b16 [%0], {%1,%2,%3,%4};" ::"r"(addr), "r"(a), "r"(b), "r"(c), "r"(d) : "memory");
}
__device__ __forceinline__ void ldmatrix4(uint32_t addr, uint32_t& a, uint32_t& b, uint32_t& c, uint32_t& d) {
  asm volatile("ldmatrix.sync.aligned.m8n8.x4.shared.b16 {%0,%1,%2,%3}, [%4];" : "=r"(a), "=r"(b), "=r"(c), "=r"(d) : "r"(addr) : "memory");
}
__device__ __forceinline__ void ldmatrix4t(uint32_t addr, uint32_t& a, uint32_t& b, uint32_t& c, uint32_t& d) {
  asm volatile("ldmatrix.sync.aligned.m8n8.x4.trans.shared.b16 {%0,%1,%2,%3}, [%4];" : "=r"(a), "=r"(b), "=r"(c), "=r"(d) : "r"(addr) : "memory");
}
__device__ __forceinline__ void mma16816(float (&d)[4], uint32_t a0, uint32_t a1, uint32_t a2, uint32_t a3, uint32_t b0, uint32_t b1) {
  asm volatile("mma.sync.aligned.m16n8k16.row.col.f32.bf16.bf16.f32 {%0,%1,%2,%3}, {%4,%5,%6,%7}, {%8,%9}, {%0,%1,%2,%3};"
               : "+f"(d[0]), "+f"(d[1]), "+f"(d[2]), "+f"(d[3]) : "r"(a0), "r"(a1), "r"(a2), "r"(a3), "r"(b0), "r"(b1));
}
__device__ __forceinline__ void sts1(uint32_t a, uint32_t v) { asm volatile("st.shared.u32 [%0], %1;" ::"r"(a), "r"(v) : "memory"); }
__device__ __forceinline__ uint4 lds4(uint32_t a) {
  uint4 v; asm volatile("ld.shared.v4.u32 {%0,%1,%2,%3}, [%4];" : "=r"(v.x), "=r"(v.y), "=r"(v.z), "=r"(v.w) : "r"(a) : "memory"); return v;
}
__device__ __forceinline__ uint2 lds2(uint32_t a) {
  uint2 v; asm volatile("ld.shared.v2.u32 {%0,%1}, [%2];" : "=r"(v.x), "=r"(v.y) : "r"(a) : "memory"); return v;
}
__device__ __forceinline__ uint32_t lds1(uint32_t a) {
  uint32_t v; asm volatile("ld.shared.u32 %0, [%1];" : "=r"(v) : "r"(a) : "memory"); return v;
}
__device__ __forceinline__ void sts2(uint32_t a, uint32_t x, uint32_t y) { asm volatile("st.shared.v2.u32 [%0], {%1,%2};" ::"r"(a), "r"(x), "r"(y) : "memory"); }
__device__ __forceinline__ void sts4(uint32_t a, uint4 v) {
  asm volatile("st.shared.v4.u32 [%0], {%1,%2,%3,%4};" ::"r"(a), "r"(v.x), "r"(v.y), "r"(v.z), "r"(v.w) : "memory");
}
__device__ __forceinline__ float silu_f(float v) { return __fdividef(v, 1.f + __expf(-v)); }
__device__ __forceinline__ uint32_t hfma2(uint32_t a, uint32_t b, uint32_t c) {
  uint32_t r; asm("fma.rn.bf16x2 %0, %1, %2, %3;" : "=r"(r) : "r"(a), "r"(b), "r"(c)); return r;
}
__device__ __forceinline__ void split_inv(float sd, uint32_t& ih, uint32_t& il) {
  const float inv = rcp(sd);
  ih = pack_bf(inv, inv);
  const float lo = inv - bf_lo(ih);
  il = pack_bf(lo, lo);
}
__device__ __forceinline__ uint32_t ln_norm(uint32_t x, uint32_t mean2, uint32_t ih, uint32_t il) {
  const uint32_t d = hsub2(x, mean2);
  return hfma2(d, ih, hmul2(d, il));
}
__device__ __forceinline__ uint32_t modul(uint32_t n, uint32_t c1, uint32_t sh) { return hadd2(hmul2(n, c1), sh); }
__device__ __forceinline__ uint32_t ln_mod(uint32_t x, uint32_t mean2, uint32_t ih, uint32_t il, uint32_t c1, uint32_t sh) {
  return modul(ln_norm(x, mean2, ih, il), c1, sh);
}

#define R8(a, i) "+f"(a[i]), "+f"(a[i + 1]), "+f"(a[i + 2]), "+f"(a[i + 3]), "+f"(a[i + 4]), "+f"(a[i + 5]), "+f"(a[i + 6]), "+f"(a[i + 7])
#define D64 "{%0,%1,%2,%3,%4,%5,%6,%7,%8,%9,%10,%11,%12,%13,%14,%15,%16,%17,%18,%19,%20,%21,%22,%23,%24,%25,%26,%27,%28,%29,%30,%31," \
            "%32,%33,%34,%35,%36,%37,%38,%39,%40,%41,%42,%43,%44,%45,%46,%47,%48,%49,%50,%51,%52,%53,%54,%55,%56,%57,%58,%59,%60,%61,%62,%63}"
template <int TB>
__device__ __forceinline__ void mma_ss(float (&d)[64], uint64_t da, uint64_t db, int sc) {
  asm volatile("{\n.reg .pred p;\nsetp.ne.b32 p, %66, 0;\n"
               "wgmma.mma_async.sync.aligned.m64n128k16.f32.bf16.bf16 " D64 ", %64, %65, p, 1, 1, 0, %67;\n}"
               : R8(d, 0), R8(d, 8), R8(d, 16), R8(d, 24), R8(d, 32), R8(d, 40), R8(d, 48), R8(d, 56)
               : "l"(da), "l"(db), "r"(sc), "n"(TB));
}
template <int TB>
__device__ __forceinline__ void mma_rs(float (&d)[64], uint32_t a0, uint32_t a1, uint32_t a2, uint32_t a3, uint64_t db, int sc) {
  asm volatile("{\n.reg .pred p;\nsetp.ne.b32 p, %69, 0;\n"
               "wgmma.mma_async.sync.aligned.m64n128k16.f32.bf16.bf16 " D64 ", {%64,%65,%66,%67}, %68, p, 1, 1, %70;\n}"
               : R8(d, 0), R8(d, 8), R8(d, 16), R8(d, 24), R8(d, 32), R8(d, 40), R8(d, 48), R8(d, 56)
               : "r"(a0), "r"(a1), "r"(a2), "r"(a3), "l"(db), "r"(sc), "n"(TB));
}
#define D128 "{%0,%1,%2,%3,%4,%5,%6,%7,%8,%9,%10,%11,%12,%13,%14,%15,%16,%17,%18,%19,%20,%21,%22,%23,%24,%25,%26,%27,%28,%29,%30,%31," \
             "%32,%33,%34,%35,%36,%37,%38,%39,%40,%41,%42,%43,%44,%45,%46,%47,%48,%49,%50,%51,%52,%53,%54,%55,%56,%57,%58,%59,%60,%61,%62,%63," \
             "%64,%65,%66,%67,%68,%69,%70,%71,%72,%73,%74,%75,%76,%77,%78,%79,%80,%81,%82,%83,%84,%85,%86,%87,%88,%89,%90,%91,%92,%93,%94,%95," \
             "%96,%97,%98,%99,%100,%101,%102,%103,%104,%105,%106,%107,%108,%109,%110,%111,%112,%113,%114,%115,%116,%117,%118,%119,%120,%121,%122,%123,%124,%125,%126,%127}"
#define R128(d, e) R8(d, 0), R8(d, 8), R8(d, 16), R8(d, 24), R8(d, 32), R8(d, 40), R8(d, 48), R8(d, 56), \
                   R8(e, 0), R8(e, 8), R8(e, 16), R8(e, 24), R8(e, 32), R8(e, 40), R8(e, 48), R8(e, 56)
__device__ __forceinline__ void mma256_ss(float (&d)[64], float (&e)[64], uint64_t da, uint64_t db, int sc) {
  asm volatile("{\n.reg .pred p;\nsetp.ne.b32 p, %130, 0;\n"
               "wgmma.mma_async.sync.aligned.m64n256k16.f32.bf16.bf16 " D128 ", %128, %129, p, 1, 1, 0, 1;\n}"
               : R128(d, e) : "l"(da), "l"(db), "r"(sc));
}
__device__ __forceinline__ void mma256_rs(float (&d)[64], float (&e)[64], uint32_t a0, uint32_t a1, uint32_t a2, uint32_t a3, uint64_t db) {
  asm volatile("{\n.reg .pred p;\nsetp.ne.b32 p, 1, 0;\n"
               "wgmma.mma_async.sync.aligned.m64n256k16.f32.bf16.bf16 " D128 ", {%128,%129,%130,%131}, %132, p, 1, 1, 1;\n}"
               : R128(d, e) : "r"(a0), "r"(a1), "r"(a2), "r"(a3), "l"(db));
}
template <int N> __device__ __forceinline__ void keep(float (&a)[N]) {
#pragma unroll
  for (int i = 0; i < N; i++) asm volatile("" : "+f"(a[i])::"memory");
}
template <int N> __device__ __forceinline__ void keep(uint32_t (&a)[N]) {
#pragma unroll
  for (int i = 0; i < N; i++) asm volatile("" : "+r"(a[i])::"memory");
}

#define STAMP(idx) do {} while (0)
#define PROF(grp, cond, idx) do {} while (0)

constexpr float SCL2 = 1.4426950408889634f * 0.08838834764831845f;

__device__ __forceinline__ void pack_p(const float (&s)[64], uint32_t (&p)[32]) {
#pragma unroll
  for (int i = 0; i < 32; i++) p[i] = pack_bf(s[2 * i], s[2 * i + 1]);
}

__device__ __forceinline__ void issue_qk(float (&s)[64], uint32_t q0, uint32_t q1, uint32_t kslot) {
  const uint64_t db = make_desc(kslot, 16, 1024), da0 = make_desc(q0, 16, 1024), da1 = make_desc(q1, 16, 1024);
#pragma unroll
  for (int kk = 0; kk < 8; kk++) mma_ss<0>(s, (kk < 4 ? da0 : da1) + (kk & 3) * 2, db + (kk >> 2) * 1024 + (kk & 3) * 2, kk != 0);
}
__device__ __forceinline__ void issue_pv(float (&o)[64], uint32_t (&p)[32], uint32_t vslot, int acc) {
  uint64_t db = make_desc(vslot, 16384, 1024);
#pragma unroll
  for (int kk = 0; kk < 8; kk++)
    mma_rs<1>(o, p[4 * kk], p[4 * kk + 1], p[4 * kk + 2], p[4 * kk + 3], db + kk * 128, kk == 0 ? acc : 1);
}

template <int H>
__device__ __forceinline__ void store_chunk(const float (&a)[64], uint32_t addr) {
#pragma unroll
  for (int i = 8 * H; i < 8 * H + 8; i += 2)
    stmatrix4(addr ^ ((i & 7) << 4), pack_bf(a[4 * i], a[4 * i + 1]), pack_bf(a[4 * i + 2], a[4 * i + 3]),
              pack_bf(a[4 * i + 4], a[4 * i + 5]), pack_bf(a[4 * i + 6], a[4 * i + 7]));
}
template <int H>
__device__ __forceinline__ void store_chunk(const float (&a)[64], float i0, float i1, uint32_t addr) {
#pragma unroll
  for (int i = 8 * H; i < 8 * H + 8; i += 2)
    stmatrix4(addr ^ ((i & 7) << 4), pack_bf(a[4 * i] * i0, a[4 * i + 1] * i0), pack_bf(a[4 * i + 2] * i1, a[4 * i + 3] * i1),
              pack_bf(a[4 * i + 4] * i0, a[4 * i + 5] * i0), pack_bf(a[4 * i + 6] * i1, a[4 * i + 7] * i1));
}
__device__ __forceinline__ float inv_quad_sum(float l) {
  l += __shfl_xor_sync(0xffffffffu, l, 1);
  l += __shfl_xor_sync(0xffffffffu, l, 2);
  return rcp(l);
}

__device__ __forceinline__ void write_table(uint32_t table, bool ca, uint32_t t, const uint4& m0, const uint4& m1) {
  float c0 = untag_sum(m0.x, m1.x), c1 = untag_sum(m0.y, m1.y), c2 = untag_sum(m0.z, m1.z), c3 = untag_sum(m0.w, m1.w);
  if (ca) { c0 = 1.f + rbf(c0); c1 = 1.f + rbf(c1); c2 = 1.f + rbf(c2); c3 = 1.f + rbf(c3); }
  const uint32_t d = table + (t >> 2) * 64 + (t & 1) * 32 + (t & 2) * 2 + (ca ? 0 : 8);
  sts1(d, pack_bf(c0, c1));
  sts1(d + 16, pack_bf(c2, c3));
}

__device__ __forceinline__ void ln_scalars(float mean, float var, float& mb, float& sd) {
  mb = rbf(mean);
  float r; asm("sqrt.approx.ftz.f32 %0, %1;" : "=f"(r) : "f"(rbf(rbf(var) + 1e-5f)));
  sd = rbf(r);
}

__global__ void __cluster_dims__(2, 1, 1) __launch_bounds__(384, 1) fused_kernel(const __grid_constant__ Maps maps, const Ptrs P) {
  extern __shared__ __align__(1024) uint8_t smem_raw[];
  const uint32_t base = smem_u32(smem_raw);
  const int tid = threadIdx.x, lane = tid & 31;
  const int warp = __shfl_sync(0xffffffffu, tid >> 5, 0);
  const int b = blockIdx.x;
  PROF(31, tid == 0, 0);

  if (b >= NMAIN) {
    float* sc = reinterpret_cast<float*>(smem_raw);
    float* red = sc + DM;
    for (int k = tid; k < DM; k += 384) sc[k] = rbf(silu_f(__bfloat162float(P.c[k])));
    __syncthreads();
    if (tid < 256) {
      const int col = 2048 + (b - NMAIN) * 1024 + (tid & 127) * 8, r0 = (tid >> 7) * 512;
      float acc[8];
#pragma unroll
      for (int e = 0; e < 8; e++) acc[e] = 0.f;
#pragma unroll 1
      for (int r = r0; r < r0 + 512; r += HU) {
        uint4 w[HU];
#pragma unroll
        for (int u = 0; u < HU; u++) w[u] = ldg_stream4(P.w_mod + (size_t)(r + u) * NMOD + col);
#pragma unroll
        for (int u = 0; u < HU; u++) {
          float s = sc[r + u];
          acc[0] += s * bf_lo(w[u].x); acc[1] += s * bf_hi(w[u].x); acc[2] += s * bf_lo(w[u].y); acc[3] += s * bf_hi(w[u].y);
          acc[4] += s * bf_lo(w[u].z); acc[5] += s * bf_hi(w[u].z); acc[6] += s * bf_lo(w[u].w); acc[7] += s * bf_hi(w[u].w);
        }
      }
      if (tid >= 128) {
#pragma unroll
        for (int e = 0; e < 8; e++) red[(tid & 127) * 8 + e] = acc[e];
      }
      const uint32_t tag = ld_relaxed(&g_epoch) % 3 + 1;
      bar_sync(1, 256);
      if (tid < 128) {
        uint32_t o[8];
#pragma unroll
        for (int e = 0; e < 8; e++) o[e] = __float_as_uint(rbf(acc[e] + red[tid * 8 + e])) | tag;
        st_relaxed4(g_mod + col, o[0], o[1], o[2], o[3]);
        st_relaxed4(g_mod + col + 4, o[4], o[5], o[6], o[7]);
        const uint4 wr = ldg_nc4(P.w_r + tid * 8);
        const uint32_t wv[4] = {wr.x, wr.y, wr.z, wr.w};
        float dsum = 0.f;
#pragma unroll
        for (int e = 0; e < 8; e++) {
          const float m = bf_hi(o[e]);
          dsum += (b == NMAIN + 2 ? rbf(1.f + m) : m) * ((e & 1) ? bf_hi(wv[e >> 1]) : bf_lo(wv[e >> 1]));
        }
#pragma unroll
        for (int k = 16; k > 0; k >>= 1) dsum += __shfl_xor_sync(0xffffffffu, dsum, k);
        if (lane == 0) st_relaxed(g_mod + (b - NMAIN) * 4 + warp, tagf(dsum, tag));
      }
    }
    PROF(2, tid == 0, 1);
    return;
  }

  const int rank = b & 1;
  const int rb = ((b >> 4) << 1) | rank, cj = (b >> 1) & 7;
  const bool late = b & 4;
  const uint32_t bfull = base + OFF_BAR, bempty = bfull + NSLOT * 8;
  const uint32_t gfull = bempty + NSLOT * 8, gempty = gfull + 32;
  const uint32_t bar_ofull = gempty + 32;
  const uint32_t bar_ofree = bar_ofull + 32;
  const uint32_t bar_par = bar_ofree + 32;
  const uint32_t bar_mod = bar_par + 8;
  const uint32_t bar_pread = bar_mod + 8;
  const uint32_t bar_xres = bar_pread + 8;
  const uint32_t bar_ring = bar_xres + 8;
  const uint32_t bar_box = bar_ring + 24;
  const uint32_t bar_go = bar_box + 96;
  const uint32_t bar_go2 = bar_go + 16;
  const uint32_t bar_cnt = bar_go + 24;
  const uint32_t xfull = bar_go + 40, xempty = xfull + 32;
  const uint32_t bar_hw = xempty + 32, bar_hx = bar_hw + 8;
  const uint32_t bar_hpub = bar_hx + 16;
  const uint32_t bar_win = bar_hpub + 16;
  const uint32_t bar_rx = bar_win + 8;
  const uint32_t bar_sel = bar_rx + 8;
  const uint32_t bar_gate = bar_sel + 8;
  const uint32_t bar_rel = bar_gate + 8;
  const uint32_t bar_od = bar_rel + 8;
  const uint32_t bar_mod2 = bar_od + 8;
  const uint32_t bar_res = bar_go + 8;
  const uint32_t stage = base + OFF_STAGE, par = base + OFF_PAR;

  if (warp == 8 && elect_one()) {
    for (int s = 0; s < NSLOT; s++) { mbar_init(bfull + s * 8, 1); mbar_init(bempty + s * 8, 16); }
    for (int s = 0; s < 4; s++) { mbar_init(gfull + s * 8, 1); mbar_init(gempty + s * 8, 16); mbar_init(xfull + s * 8, 1); mbar_init(xempty + s * 8, 8); mbar_init(bar_ofree + s * 8, 1); mbar_init(bar_ofull + s * 8, 128); }
    mbar_init(bar_par, 64); mbar_init(bar_mod, 256); mbar_init(bar_pread, 2); mbar_init(bar_xres, 1);
    mbar_init(bar_ring, 8); mbar_init(bar_ring + 8, 8); mbar_init(bar_ring + 16, 8);
    mbar_init(bar_go, 1); mbar_init(bar_go2, 1); mbar_init(bar_cnt, 1); mbar_init(bar_cnt + 8, 1); mbar_init(bar_hpub, 8); mbar_init(bar_hpub + 8, 8); mbar_init(bar_res, 1); mbar_init(bar_win, 1); mbar_init(bar_rx, 1); mbar_init(bar_sel, 64); mbar_init(bar_gate, 8); mbar_init(bar_rel, 8); mbar_init(bar_od, 1); mbar_init(bar_mod2, 64);
    for (int s = 0; s < 12; s++) mbar_init(bar_box + s * 8, 1);
    asm volatile("fence.mbarrier_init.release.cluster;" ::: "memory");
    prefetch_map(&maps.x); prefetch_map(&maps.wq); prefetch_map(&maps.k); prefetch_map(&maps.v);
  }
  if (warp == 9 && elect_one()) {
    mbar_init(bar_hw, 1); mbar_init(bar_hx, 1); mbar_init(bar_hx + 8, 1);
    asm volatile("fence.mbarrier_init.release.cluster;" ::: "memory");
    mbar_expect_tx(bar_hw, 32768);
    mbar_expect_tx(bar_hx, 16384);
    mbar_expect_tx(bar_hx + 8, 16384);
    const __nv_bfloat16* xs = P.x + (size_t)(rb * 128 + cj * 16) * DM;
    bulk_load(base + 2 * GST_BYTES, xs, 16384, bar_hx);
    if (!late) {
      tma2d(stage, &maps.wm, (b >> 1) * 32, rank * 512, bar_hw);
      tma2d(stage + 16384, &maps.wm, (b >> 1) * 32, rank * 512 + 256, bar_hw);
    } else {
      prefetch_map(&maps.wm);
    }
    bulk_load(base + 3 * GST_BYTES, xs + 8 * DM, 16384, bar_hx + 8);
  }
  cluster_arrive();

  if (warp >= 8) {
    asm volatile("setmaxnreg.dec.sync.aligned.u32 40;");
    if (warp < 10) bar_arrive(1, 320);
    const uint32_t epoch = ld_relaxed(&g_epoch);
    cluster_wait();
    if (warp == 8) {
      const int kvrow = (cj >> 1) * SK + (SK - WIN);
      int wch = cj * 8 + rank * 2;
#pragma unroll 1
      for (int ps = 0; ps < 3; ps++) {
        const CUtensorMap* mw = ps == 2 ? &maps.wo : &maps.wq;
        const uint32_t xt = ps == 1 ? XT1 : XT2, wt = ps == 0 ? WT0 : (ps == 1 ? WT1 : WT2);
        const int nst = ps == 2 ? 32 : 16;
#pragma unroll 1
        for (int i = 0; i < nst; i++) {
          const uint32_t bf = gfull + (i & 3) * 8;
          const int kt = ps == 2 ? (((cj & 1) * 4 + ((i >> 1) & 3)) * 4 + (i >> 3)) * 2 + (i & 1) : (ps ? i : slice_of(i) + (b & 14)) & 15;
          const uint32_t wd = base + unit_of(wt, i & 3) + rank * UNIT, xd = base + unit_of(xt, i & 3);
          const uint8_t* xs = g_act + (uint32_t)(rb * 80 + (ps - 1) * 16 + kt) * UNIT;
          if (ps == 0 && i == HD) mbar_wait(bar_mod, 0);
          const bool xfirst = ps && i < 2;
          if (ps == 2 && i == 0) mbar_wait(bar_ofree + 24, 0);
          if (i == 0) fence_async();
          mbar_wait(gempty + (i & 3) * 8, ((i >> 2) & 1) ^ 1);
          if (elect_one()) {
            mbar_expect_tx(bf, ps ? GST_BYTES : 2 * UNIT);
            if (xfirst) bulk_load_stream(xd, xs, UNIT, bf);
          }
          if (ps && i < 4) mbar_wait(bempty + i * 8, 1);
          if (elect_one()) tma3d_mc<true>(wd, mw, 0, (i == 31 ? kt ^ (rank * 32) : kt) * 64, i == 31 ? cj * 2 : wch, bf);
          if (ps) {
            if (i == 16 || i == 24) { mbar_wait(bar_cnt + i - 16, 0); fence_async(); }
            if (i == RES0) mbar_wait(bar_res, 0);
            if (i == 2) mbar_wait(bar_ofree + (ps - 1) * 16, 0);
            if (elect_one()) {
              if (i == 31) bulk_load(xd, xs, UNIT, bf); else if (!xfirst) bulk_load_stream(xd, xs, UNIT, bf);
              mbar_arrive_pred(bar_go, i == GOST - 1);
              if (PG0 < 16) mbar_arrive_pred(bar_go2, ps == 1 && i == PG0);
              mbar_arrive_pred(bar_od, i == (ps == 1 ? ODS1 : ODS));
              if (i == RES0) mbar_expect_tx(bar_xres, 32768);
              if (i == RES0 || i == RES1) tma2d(base + OFF_RES + (i == RES1) * UNIT, &maps.x, cj * 128 + (i == RES1) * 64, rb * 128, bar_xres);
            }
          }
        }
        if (ps == 2) break;
        wch = ps ? ((wch >> 3) ^ rank) * 2 : wch + 4;
#pragma unroll 1
        for (int u = 0; u < 16; u++) {
          const bool isk = (u == 0) || ((u & 1) && u < 15);
          const int blk = (isk ? (u + 1) >> 1 : (u == 15 ? 7 : (u >> 1) - 1)) & 3;
          const uint32_t sl = base + unit_of(ps ? AT1 : AT0, u & 3) + rank * UNIT, bf = bfull + (u & 3) * 8;
          if (u < 4) mbar_wait(gempty + ((u + 1) >> 1) * 8, 1);
          mbar_wait(bempty + (u & 3) * 8, ((u >> 2) & 1) ^ 1);
          if (elect_one()) {
            mbar_arrive_pred(bar_go2, ps && u + 16 == PG0);
            mbar_expect_tx(bf, SLOT_BYTES);
            tma3d_mc<false>(sl, isk ? &maps.k : &maps.v, 0, kvrow + blk * 128, rank, bf);
          }
        }
      }
      if (elect_one()) mbar_expect_tx(bar_rx, UNIT);
      mbar_wait(bar_rel, 0);
      if (elect_one()) {
        bulk_load_stream(base + UNIT, g_act + (uint32_t)(rb * 80 + 16 + 63 - (cj & 1) * 32) * UNIT, UNIT, bar_rx);
      }
      if (b < NFFN) {
#pragma unroll 1
        for (int u = 0; u < 12; u++) {
          const uint32_t dst = base + unit_of(u < 4 ? FT_G : (u < 8 ? FT_U : FT_D), u & 3);
          if (elect_one()) mbar_expect_tx(bar_box + u * 8, UNIT);
          if (u == FB0 || u == FB1 || u == FB2) mbar_wait(bar_ring + (u == FB2 ? 16 : u == FB1 ? 8 : 0), 0);
          const int fp = u < FPB ? FPACE0 : FPACE;
          if (u >= fp) mbar_wait(bar_box + (u - fp) * 8, 0);
          if (elect_one()) {
            if (u < 8) tma2d(dst, u < 4 ? &maps.wg : &maps.wu, b * 32, (u & 3) * 256, bar_box + u * 8);
            else tma3d(dst, &maps.wd, 0, b * 32, (u - 8) * 4, bar_box + u * 8);
          }
        }
      }
    } else if (warp == 9) {
      const uint32_t target = 8 * (epoch + 1);
      uint32_t hmask = 0;
#pragma unroll 1
      for (int i = 0; i < 16; i++) {
        if (i == HDX) mbar_wait(bar_mod, 0);
        const int kt = (2 * cj + slice_of(i)) & 15;
        const uint32_t need = i == 15 ? 0xffffu : 1u << kt;
        if (i >= NRS && (hmask & need) != need) {
          uint32_t n = 0;
          do { hmask = __ballot_sync(0xffffffffu, ld_acquire(&g_cnt_h[rb * 32 + (lane & 15)]) == epoch + 1); watchdog(n); } while ((hmask & need) != need);
          PROF(1, lane == 0 && i == NRS, 26);
          fence_async();
        }
        mbar_wait(xempty + (i & 3) * 8, ((i >> 2) & 1) ^ 1);
        if (elect_one()) {
          mbar_expect_tx(xfull + (i & 3) * 8, UNIT);
          if (i < NRS) tma2d(base + (i & 3) * GST_BYTES, &maps.x, kt * 64, rb * 128, xfull + (i & 3) * 8);
          else bulk_load_stream(base + (i & 3) * GST_BYTES, g_act + (uint32_t)(rb * 80 + kt) * UNIT, UNIT, xfull + (i & 3) * 8);
        }
      }
      prefetch_map(&maps.wo);
#pragma unroll 1
      for (int t = 0; t < 4; t++) {
        if (t & 1) mbar_wait(bar_od, t >> 1);
#pragma unroll 1
        for (int p = 0; p < 32768 / OPS; p++) {
          const uint32_t w = p / (16384 / OPS), c = (p / (8192 / OPS)) & 1, off = w * 8192 + (p % (8192 / OPS)) * OPS;
          mbar_wait(bar_ofull + (t & 1) * 16 + w * 8, t >> 1);
          if (elect_one()) {
            bulk_store(g_act + (uint32_t)(rb * 80 + 16 + (cj * 4 + t) * 2 + c) * UNIT + off, base + unit_of(QT, 2 * t + c) + off, OPS);
            asm volatile("cp.async.bulk.commit_group;" ::: "memory");
            asm volatile("cp.async.bulk.wait_group.read %0;" ::"n"(OFL) : "memory");
          }
        }
        if (elect_one()) {
          asm volatile("cp.async.bulk.wait_group.read 0;" ::: "memory");
          mbar_arrive(t < 3 ? bar_ofree + t * 8 : bar_res);
          asm volatile("cp.async.bulk.wait_group 0;" ::: "memory");
          fence_async();
          red_release(&g_cnt_o[((rb * 4 + t) * 2 + (cj >> 2)) * 32], 2);
        }
        if (t) {
          wait_counter(&g_cnt_o[(rb * 8 + 2 * t + (cj & 1)) * 32], target);
          if (t & 1) wait_counter(&g_cnt_o[(rb * 8 + (t == 1 ? cj & 1 : 7 - (cj & 1))) * 32], target);
          if (elect_one()) mbar_arrive(t == 1 ? bar_ofree + 24 : bar_cnt + t * 8 - 16);
        }
      }
      PROF(2, lane == 0, 27);
      const uint32_t tag = epoch % 3 + 1;
      const uint32_t* inbox = g_cand + (lane & 15);
      mbar_wait(bar_ring + 16, 0);
      uint32_t c0 = ld_relaxed(inbox), n = 0;
#define CAND_STEP(cv)                                                                                        \
      {                                                                                                      \
        const bool valid = (cv & 3u) == tag, all = __all_sync(0xffffffffu, valid);                           \
        const uint32_t best = __reduce_max_sync(0xffffffffu, valid ? cv : 0u);                               \
        const uint32_t blk = __ffs(__ballot_sync(0xffffffffu, cv == best)) - 1;                              \
        if (best) sts2(par + PAR_CONST + 56, best, (blk << 7 | (~best >> 2 & 127)) | (all ? 0x1800 : 0x800)); \
        if (all) break;                                                                                      \
        cv = ld_relaxed(inbox);                                                                              \
      }
      while (true) { CAND_STEP(c0) watchdog(n); }
    } else {
      const int t2 = tid - 320;
      if (late && warp == 10) {
        if (HWB >= 0) mbar_wait(bar_hx + HWB * 8, 0);
        if (elect_one()) {
          tma2d(stage, &maps.wm, (b >> 1) * 32, rank * 512, bar_hw);
          tma2d(stage + 16384, &maps.wm, (b >> 1) * 32, rank * 512 + 256, bar_hw);
        }
      }
      {
        const uint32_t tag = epoch % 3 + 1;
        mbar_wait(bar_hx + 8, 0);
        mbar_wait(bar_hw, 0);
        {
          const uint32_t t7 = (warp & 1) * 64 + (lane >> 4) * 32 + 16 + (lane & 15);
          const uint32_t* pm = g_modp + ((cj * 128 + t7 * 4) & (DM - 1));
          uint4 m0, m1, m2, m3;
          uint32_t n = 0;
          do {
            m0 = ld_relaxed4(pm); m1 = ld_relaxed4(pm + 2 * DM); m2 = ld_relaxed4(pm + DM); m3 = ld_relaxed4(pm + 3 * DM);
            watchdog(n);
          } while (!__all_sync(0xffffffffu, tag_ok(m0, tag) && tag_ok(m1, tag) && tag_ok(m2, tag) && tag_ok(m3, tag)));
          write_table(par, false, t7, m0, m1);
          write_table(par, true, t7, m2, m3);
          mbar_arrive(bar_mod2);
        }
      }
      mbar_wait(bar_hpub + (warp & 1) * 8, 0);
      PROF(1, t2 == 0, 24);
#pragma unroll 1
      for (int c = 0; c < 8; c++) {
        const uint32_t off = (warp & 1) * UNIT + c * 2048 + lane * 16;
        uint8_t* dst = g_act + (uint32_t)(rb * 80 + cj * 2) * UNIT + off;
        const uint4 v0 = lds4(stage + off), v1 = lds4(stage + off + 512), v2 = lds4(stage + off + 1024), v3 = lds4(stage + off + 1536);
        stg4(dst, v0); stg4(dst + 512, v1); stg4(dst + 1024, v2); stg4(dst + 1536, v3);
      }
      __syncwarp();
      PROF(1, t2 == 0, 15);
      if (lane == 0) {
        mbar_arrive(bar_pread);
        red_release(&g_cnt_h[rb * 32 + cj * 2 + (warp & 1)], 1);
        PROF(1, t2 == 0, 25);
        prefetch_map(&maps.wg); prefetch_map(&maps.wu); prefetch_map(&maps.wd); prefetch_map(&maps.out);
      }
      __syncwarp();
      if (b < NFFN) {
        mbar_wait(bar_go2, 0);
        const __nv_bfloat16* pg = ((b & 1) ? P.w_up : P.w_gate) + (b >> 1) * 64 + (size_t)t2 * FF;
        const __nv_bfloat16* pd = P.w_down + (size_t)b * 32768 + t2 * 64;
        PROF(2, t2 == 0, 13);
#pragma unroll 1
        for (int i = 0; i < WN; i += WB) {
          uint32_t v[WB];
#pragma unroll
          for (int u = 0; u < WB; u++) {
            const int k = i + u;
            asm volatile("ld.global.cg.L2::128B.u32 %0, [%1];" : "=r"(v[u]) : "l"(k < 16 ? pg + (size_t)k * 64 * FF : pd + (k - 16) * 4096));
          }
#pragma unroll
          for (int u = 1; u < WB; u++) v[0] ^= v[u];
          sts1(par + PAR_SINK + t2 * 4, v[0]);
        }
        PROF(2, t2 == 0, 14);
      }
      const uint32_t tag = epoch % 3 + 1;
      mbar_wait(bar_go, 0);
      bar_sync(4, 64);
      if (warp == 10) {
        const uint32_t* src = g_mod + 2 * DM + cj * 128 + lane * 4;
        const uint2 wr = *reinterpret_cast<const uint2*>(P.w_r + cj * 128 + lane * 4);
        uint4 vga, vsb, vcb, vgb;
        uint32_t n = 0;
        do {
          vga = ld_relaxed4(src); vsb = ld_relaxed4(src + DM); vcb = ld_relaxed4(src + 2 * DM); vgb = ld_relaxed4(src + 3 * DM);
          watchdog(n);
        } while (!__all_sync(0xffffffffu, tag_ok(vga, tag) && tag_ok(vsb, tag) && tag_ok(vcb, tag) && tag_ok(vgb, tag)));
        const float c0 = rbf(1.f + bf_hi(vcb.x)), c1 = rbf(1.f + bf_hi(vcb.y)), c2 = rbf(1.f + bf_hi(vcb.z)), c3 = rbf(1.f + bf_hi(vcb.w));
        const float a0 = c0 * bf_lo(wr.x), a1 = c1 * bf_hi(wr.x), a2 = c2 * bf_lo(wr.y), a3 = c3 * bf_hi(wr.y);
        const uint32_t h0 = pack_bf(a0, a1), h1 = pack_bf(a2, a3);
        const uint32_t t1 = par + PAR_T1 + (lane >> 2) * 64 + (lane & 1) * 32 + (lane & 2) * 2;
        sts1(t1, h0); sts1(t1 + 8, pack_bf(a0 - bf_lo(h0), a1 - bf_hi(h0)));
        sts1(t1 + 16, h1); sts1(t1 + 24, pack_bf(a2 - bf_lo(h1), a3 - bf_hi(h1)));
        const uint32_t tg = par + PAR_SINK + (lane >> 3) * 64 + (lane & 1) * 32 + (lane & 6) * 2;
        sts1(tg, __byte_perm(vga.x, vga.y, 0x7632)); sts1(tg + 16, __byte_perm(vga.z, vga.w, 0x7632));
        sts4(par + PAR_T2 + lane * 32, make_uint4(pack_bf(c0, c1), __byte_perm(vsb.x, vsb.y, 0x7632), __byte_perm(vgb.x, vgb.y, 0x7632), __byte_perm(vga.x, vga.y, 0x7632)));
        sts4(par + PAR_T2 + lane * 32 + 16, make_uint4(pack_bf(c2, c3), __byte_perm(vsb.z, vsb.w, 0x7632), __byte_perm(vgb.z, vgb.w, 0x7632), __byte_perm(vga.z, vga.w, 0x7632)));
      } else {
        const uint4 g = poll4((lane & 2) ? g_mod + 8 - (lane & 1) * 4 : g_mod + 5 * DM + b * 8 + (lane & 1) * 4, tag);
        sts1(par + PAR_CONST + 60, 0);
        if (lane < 2) sts4(par + PAR_CONST + 16 + lane * 16, g);
        else if (lane < 4) sts2(par + PAR_CONST + (lane - 2) * 8, __float_as_uint(untag_sum(g.x, g.y) + untag_sum(g.z, g.w)), epoch);
      }
      __syncwarp();
#pragma unroll 4
      for (int q = 0; q < 32; q++) st_b128(g_xch + ((size_t)b * 8 * 256 + q * 64 + t2) * 4, (epoch & 1) << 16, 0, 0, 0);
      for (int q = 0; q < 2; q++) st_relaxed4(g_stats + ((size_t)cj * SEQ + rb * 128 + q * 64 + t2) * 4, 0, 0, 0, 0);
      if (b < NFFN)
        for (int q = 0; q < 4; q++) st_relaxed4(g_ypart + ((size_t)(q * 32 + (t2 >> 1)) * NFFN + b) * 8 + (t2 & 1) * 4, 0, 0, 0, 0);
      st_relaxed4(g_row + rb * 2 * DM + (t2 >> 5) * DM + cj * 128 + (t2 & 31) * 4, 0, 0, 0, 0);
      __threadfence();
      mbar_arrive(bar_par);
      mbar_wait(bar_gate, 0);
      uint32_t have = 0, n = 0;
      while (true) {
        const uint32_t st = lds1(par + PAR_CONST + 60) >> 7;
        if ((st & 31) != have) {
          const uint32_t* hsrc = g_row + (st & 15) * 2 * DM + t2 * 4;
          uint4 hv[4];
          bool ok = true;
#pragma unroll
          for (int i = 0; i < 4; i++) hv[i] = ld_pairs(hsrc + i * 256);
#pragma unroll
          for (int i = 0; i < 4; i++) {
            sts2(base + ((FT_G >> i * 4) & 15) * UNIT + (warp & 1) * 8192 + 256 + lane * 8, hv[i].x, hv[i].z);
            ok = ok && hv[i].y == tag && hv[i].w == tag;
          }
          have = __all_sync(0xffffffffu, ok) ? st & 31 : 0;
        }
        if ((st ^ have) == 32) break;
        watchdog(n);
      }
      mbar_arrive(bar_sel);
    }
    __syncwarp();
    cluster_arrive();
    {
      const uint32_t tag = epoch % 3 + 1, t3 = tid - 256;
      mbar_wait(bar_win, 0);
      uint2 win = lds2(par + PAR_CONST + 56);
      win.y &= 0x7ff;
      const uint32_t* fsrc = g_row + (win.y >> 7) * 2 * DM + (b >> 1) * 16 + (t3 & 3) * 4 + (b & 1) * 2;
      const uint32_t* ysrc = g_ypart + (size_t)b * NFFN * 8 + min(t3, NFFN - 1) * 4;
      uint2 fh = ld_pair(fsrc), fx = ld_pair(fsrc + DM);
      if (PSL) __nanosleep(PSL);
      uint4 ya = ld_relaxed4(ysrc), yb = ld_relaxed4(ysrc + NFFN * 4);
      const float rwin = __uint_as_float(((int)win.x < 0 ? win.x & 0x7fffffffu : ~win.x) & ~0x1ffu);
      const float rs = rbf(rcp(1.f + __expf(-rbf(rwin))));
      uint32_t n = 0;
      while (__any_sync(0xffffffffu, fh.y != tag || fx.y != tag)) { fh = ld_pair(fsrc); fx = ld_pair(fsrc + DM); watchdog(n); }
      while (!__all_sync(0xffffffffu, tag_ok(ya, tag) && tag_ok(yb, tag))) {
        if (!tag_ok(ya, tag)) ya = ld_relaxed4(ysrc);
        if (!tag_ok(yb, tag)) yb = ld_relaxed4(ysrc + NFFN * 4);
        watchdog(n);
      }
      __syncwarp();
      PROF(8, t3 == 0, 5);
      float y0 = untag_sum(ya.x, yb.x), y1 = untag_sum(ya.y, yb.y), y2 = untag_sum(ya.z, yb.z), y3 = untag_sum(ya.w, yb.w);
      const bool u1 = lane & 2, u2 = lane & 4;
      y0 = (u1 ? y2 : y0) + __shfl_xor_sync(0xffffffffu, u1 ? y0 : y2, 2);
      y1 = (u1 ? y3 : y1) + __shfl_xor_sync(0xffffffffu, u1 ? y1 : y3, 2);
      y0 = (u2 ? y1 : y0) + __shfl_xor_sync(0xffffffffu, u2 ? y0 : y1, 4);
      y0 += __shfl_xor_sync(0xffffffffu, y0, 8);
      if (!(lane & 8)) sts1(par + PAR_RED + 64 + (t3 >> 4) * 32 + ((lane & 1) * 4 + (lane & 2) + ((lane >> 2) & 1)) * 4, __float_as_uint(y0));
      bar_sync(4, 128);
      if (t3 < 4) {
        y0 = 0.f; y1 = 0.f;
#pragma unroll
        for (int w4 = 0; w4 < 7; w4++) {
          const uint2 v = lds2(par + PAR_RED + 64 + w4 * 32 + t3 * 8);
          y0 += __uint_as_float(v.x); y1 += __uint_as_float(v.y);
        }
        const uint2 gv = lds2(par + PAR_CONST + 16 + t3 * 8);
        const uint32_t upd = hmul2(pack_bf(y0, y1), pack_bf(rs, rs));
        *reinterpret_cast<uint32_t*>(P.out + (size_t)win.y * DM + b * 8 + t3 * 2) =
            hadd2(fx.x, hmul2(__byte_perm(gv.x, gv.y, 0x7632), hadd2(fh.x, upd)));
        if (b == 0 && t3 == 0) st_relaxed(&g_epoch, epoch + 1);
      }
      PROF(31, t3 == 0, 36);
    }
    cluster_wait();
  } else {
    const int wg = warp >> 2;

    uint32_t tag;
    {
      uint32_t* const pmod = g_modp + rank * 2 * DM + (b >> 1) * 32 + lane;
      uint32_t* const pln = g_ln1 + (rb * 128 + cj * 16 + warp) * 4;
      uint32_t sc[8];
#pragma unroll
      for (int k = 0; k < 8; k++) sc[k] = ldg_nc1(P.c + rank * 512 + warp * 64 + k * 8 + (lane & 3) * 2);
      const uint32_t epoch = ld_relaxed(&g_epoch);
      if (warp == 0) st_relaxed(pmod, 0);
      if (lane == 0) { st_b128(pln, 0, 0, 0, 0); st_b128(pln + 32, 0, 0, 0, 0); }
      asm volatile("setmaxnreg.inc.sync.aligned.u32 232;");
      bar_sync(1, 320);
#pragma unroll
      for (int k = 0; k < 8; k++) sc[k] = pack_bf(silu_f(bf_lo(sc[k])), silu_f(bf_hi(sc[k])));
      keep(sc);
      tag = epoch % 3 + 1;
#pragma unroll
      for (int part = 0; part < 4; part++) {
        if (!(part & 1)) {
          const uint32_t xa = base + (2 + part / 2) * GST_BYTES + warp * 2048 + lane * 16;
          mbar_wait(bar_hx + part * 4, 0);
          float s0 = 0.f, s1 = 0.f, q0 = 0.f, q1 = 0.f;
#pragma unroll
          for (int q = 0; q < 4; q++) {
            const uint4 xv = lds4(xa + q * 512);
            const uint32_t u[4] = {xv.x, xv.y, xv.z, xv.w};
#pragma unroll
            for (int e = 0; e < 4; e++) { const float lo = bf_lo(u[e]), hi = bf_hi(u[e]); s0 += lo; s1 += hi; q0 += lo * lo; q1 += hi * hi; }
          }
          s0 += s1; q0 += q1;
#pragma unroll
          for (int o = 16; o > 0; o >>= 1) { s0 += __shfl_xor_sync(0xffffffffu, s0, o); q0 += __shfl_xor_sync(0xffffffffu, q0, o); }
          const float mean = s0 * (1.f / DM);
          float mb, sd;
          ln_scalars(mean, fmaxf(q0 * (1.f / DM) - mean * mean, 0.f), mb, sd);
          uint32_t ih, il;
          split_inv(sd, ih, il);
          if (lane == 0) st_b128(pln + part * 16, pack_bf(mb, mb), ih, il, tag);
          PROF(1, tid == 0 && part == 2, 4);
        } else if (late == (part == 3)) {
          const uint32_t fr = (lane & 7) + (lane >> 4) * 8, tq = lane & 3;
          const uint32_t wa = stage + warp * 4096 + fr * 64 + ((((lane >> 3) & 1) ^ ((fr >> 1) & 3)) << 4);
          float d0[4] = {0.f, 0.f, 0.f, 0.f}, d1[4] = {0.f, 0.f, 0.f, 0.f};
          mbar_wait(bar_hw, 0);
#pragma unroll
          for (int ks = 0; ks < 4; ks++) {
            uint32_t w[8];
            ldmatrix4t(wa + ks * 1024, w[0], w[1], w[2], w[3]);
            ldmatrix4t((wa ^ 32) + ks * 1024, w[4], w[5], w[6], w[7]);
            mma16816(d0, w[0], w[1], w[2], w[3], sc[2 * ks], sc[2 * ks + 1]);
            mma16816(d1, w[4], w[5], w[6], w[7], sc[2 * ks], sc[2 * ks + 1]);
          }
          sts1(base + 2 * GST_BYTES + warp * 2048 + (tq * 8 + (lane >> 2)) * 4, __float_as_uint((tq & 2) ? ((tq & 1) ? d1[2] : d1[0]) : ((tq & 1) ? d0[2] : d0[0])));
          bar_sync(1, 256);
          if (warp == 0) {
            float s = 0.f;
#pragma unroll
            for (int w8 = 0; w8 < 8; w8++) s += __uint_as_float(lds1(base + 2 * GST_BYTES + w8 * 2048 + lane * 4));
            st_relaxed(pmod, (__float_as_uint(s) & ~3u) | tag);
          }
          PROF(1, tid == 0, 3);
        }
      }
      cluster_wait();
      if (wg == 1) bar_arrive(2, 256);
    }

    float f0 = 0.f, f1 = 0.f;
    const uint32_t rempty = lane < 2 ? mapa(bempty, lane & 1) : 0;
    constexpr uint32_t GE = NSLOT * 8 + 32;
    float o[64], s[64];
#pragma unroll 1
    for (int ps = 0; ps < 3; ps++) {
      {
        const uint32_t xt = ps == 1 ? XT1 : XT2, wt = ps == 1 ? WT1 : WT2;
        const int nst = ps == 2 ? 28 : 14;
        if (ps == 0) {
          float ga[64], gb[64];
#pragma unroll
          for (int i = 0; i < 64; i++) { ga[i] = 0.f; gb[i] = 0.f; }
          uint32_t a[2][16];
          const uint32_t l = fresh_lane();
          uint32_t fa[4];
#pragma unroll
          for (int kk = 0; kk < 4; kk++) fa[kk] = (base + wg * 8192 + frag_offset(warp)) ^ (kk * 32);
          const uint32_t mt = par + (l & 3) * 16;
          auto fetch = [&](int i, uint32_t (&f)[16], uint32_t z) {
            mbar_wait(xfull + (i & 3) * 8, i >> 2);
#pragma unroll
            for (int kk = 0; kk < 4; kk++) ldmatrix4(fa[kk] + (i & 3) * GST_BYTES + z, f[4 * kk], f[4 * kk + 1], f[4 * kk + 2], f[4 * kk + 3]);
          };
          const bool oddw = warp & 2;
          uint4 r0, r1;
          {
            const uint32_t t7 = (warp & 1) * 64 + (l >> 4) * 32 + (l & 15);
            const uint32_t* pm = g_modp + wg * DM + ((cj * 128 + t7 * 4) & (DM - 1));
            const uint32_t* pr = g_ln1 + (rb * 128 + warp * 16 + (l >> 2)) * 4;
            uint4 m0 = make_uint4(tag, tag, tag, tag), m1 = m0;
            if (!oddw) { m0 = ld_relaxed4(pm); m1 = ld_relaxed4(pm + 2 * DM); }
            r0 = ld_b128(pr); r1 = ld_b128(pr + 32);
            fetch(0, a[0], 0); fetch(1, a[1], 0);
            uint32_t n = 0;
            bool written = false;
#pragma unroll 1
            while (true) {
              uint32_t miss;
              asm volatile("{ .reg .pred p0, p1, p2, p3; .reg .b32 t, u;\n"
                           "lop3.b32 t, %1, %2, %19, 0x7e; lop3.b32 u, %3, %4, %19, 0x7e; or.b32 t, t, u; and.b32 t, t, 3; setp.ne.u32 p0, t, 0;\n"
                           "lop3.b32 t, %5, %6, %19, 0x7e; lop3.b32 u, %7, %8, %19, 0x7e; or.b32 t, t, u; and.b32 t, t, 3; setp.ne.u32 p1, t, 0;\n"
                           "setp.ne.u32 p2, %12, %19; setp.ne.u32 p3, %16, %19;\n"
                           "@p0 ld.relaxed.gpu.global.v4.u32 {%1, %2, %3, %4}, [%17];\n"
                           "@p1 ld.relaxed.gpu.global.v4.u32 {%5, %6, %7, %8}, [%17 + 8192];\n"
                           "@p2 ld.relaxed.gpu.global.v4.u32 {%9, %10, %11, %12}, [%18];\n"
                           "@p3 ld.relaxed.gpu.global.v4.u32 {%13, %14, %15, %16}, [%18 + 128];\n"
                           "or.pred p0, p0, p1; or.pred p2, p2, p3; vote.sync.any.pred p0, p0, 0xffffffff; vote.sync.any.pred p2, p2, 0xffffffff;\n"
                           "selp.u32 t, 1, 0, p0; selp.u32 u, 2, 0, p2; or.b32 %0, t, u; }"
                           : "=r"(miss), "+r"(m0.x), "+r"(m0.y), "+r"(m0.z), "+r"(m0.w), "+r"(m1.x), "+r"(m1.y), "+r"(m1.z), "+r"(m1.w),
                             "+r"(r0.x), "+r"(r0.y), "+r"(r0.z), "+r"(r0.w), "+r"(r1.x), "+r"(r1.y), "+r"(r1.z), "+r"(r1.w)
                           : "l"(pm), "l"(pr), "r"(tag) : "memory");
              if (!(miss & 1) && !written) {
                written = true;
                if (!oddw) write_table(par, wg, t7, m0, m1);
                mbar_arrive(bar_mod);
              }
              if (!miss) break;
              watchdog(n);
            }
          }
          const uint32_t zero = r0.w ^ tag;
          auto normalize = [&](uint32_t (&f)[16]) {
#pragma unroll
            for (int k = 0; k < 16; k += 2) { f[k] = ln_norm(f[k], r0.x, r0.y, r0.z); f[k + 1] = ln_norm(f[k + 1], r1.x, r1.y, r1.z); }
          };
          auto modulate = [&](int i, uint32_t (&f)[16]) {
#pragma unroll
            for (int kk = 0; kk < 4; kk++) {
              const uint4 m = lds4(mt + slice_of(i) * 256 + kk * 64);
              f[4 * kk] = MODUL(f[4 * kk], m.x, m.z); f[4 * kk + 1] = MODUL(f[4 * kk + 1], m.x, m.z);
              f[4 * kk + 2] = MODUL(f[4 * kk + 2], m.y, m.w); f[4 * kk + 3] = MODUL(f[4 * kk + 3], m.y, m.w);
            }
            keep(f);
            mbar_arrive_pred(xempty + (i & 3) * 8, l == 0);
          };
          auto publish = [&](int u, uint32_t (&f)[16]) {
#pragma unroll
            for (int kk = 0; kk < 4; kk++) stmatrix4(fa[kk] + OFF_STAGE + u * UNIT, f[4 * kk], f[4 * kk + 1], f[4 * kk + 2], f[4 * kk + 3]);
            __syncwarp();
            mbar_arrive_pred(bar_hpub + u * 8, l == 0);
          };
          auto multiply = [&](int i, uint32_t (&f)[16]) {
            mbar_wait(gfull + (i & 3) * 8, i >> 2);
            const uint64_t db = make_desc(base + (i & 3) * GST_BYTES + UNIT, 8192, 1024);
            wg_fence();
#pragma unroll
            for (int kk = 0; kk < 4; kk++) mma256_rs(ga, gb, f[4 * kk], f[4 * kk + 1], f[4 * kk + 2], f[4 * kk + 3], db + kk * 128);
            wg_commit();
          };
          auto next = [&](int i, uint32_t (&f)[16]) {
            wg_wait<1>();
            mbar_arrive_cl(rempty, GE + ((i + 2) & 3) * 8);
            uint32_t z = zero;
#pragma unroll
            for (int k = 0; k < 16; k += 2) asm volatile("lop3.b32 %0, %1, %2, %0, 0xA8;" : "+r"(z) : "r"(f[k]), "r"(f[k + 1]));
            fetch(i, f, z);
            normalize(f);
            if (M2L && i == 2) { keep(f); mbar_wait(bar_mod2, 0); }
            modulate(i, f); multiply(i, f);
          };
          normalize(a[0]); normalize(a[1]);
          keep(a[0]); keep(a[1]);
          mbar_wait(bar_mod, 0);
          PROF(1, tid == 0, 2);
          modulate(0, a[0]); multiply(0, a[0]); publish(0, a[0]);
          modulate(1, a[1]); multiply(1, a[1]);
          if (!M2L) mbar_wait(bar_mod2, 0);
#pragma unroll 1
          for (int i = 2; i < NRS; i += 2) {
            next(i, a[0]);
            if (i == 2) publish(1, a[0]);
            next(i + 1, a[1]);
          }
          wg_wait<1>();
          mbar_arrive_cl(rempty, GE + ((NRS + 2) & 3) * 8);
#pragma unroll 1
          for (int i = NRS; i < 14; i++) {
            mbar_wait(xfull + (i & 3) * 8, (i >> 2) & 1);
            mbar_wait(gfull + (i & 3) * 8, (i >> 2) & 1);
            const uint32_t xa = base + (i & 3) * GST_BYTES;
            const uint64_t da = make_desc(xa + wg * 8192, 16, 1024), db = make_desc(xa + UNIT, 8192, 1024);
            if (i == 13) bar_sync(2 + wg, 256);
            wg_fence();
#pragma unroll
            for (int kk = 0; kk < 4; kk++) mma256_ss(ga, gb, da + kk * 2, db + kk * 128, 1);
            wg_commit();
            if (i == 13) bar_arrive(3 - wg, 256);
            wg_wait<1>();
            uint32_t z = zero;
#pragma unroll
            for (int k = 0; k < 16; k += 2) asm volatile("lop3.b32 %0, %1, %2, %0, 0xA8;" : "+r"(z) : "r"(a[1][k]), "r"(a[1][k + 1]));
            mbar_arrive_cl(rempty, GE + ((i + 3) & 3) * 8 + z);
            mbar_arrive_pred(xempty + ((i + 3) & 3) * 8, l == 0 && i != NRS);
          }
          mbar_wait(xfull + 16, 1);
          wg_wait<0>();
          keep(ga); keep(gb);
#pragma unroll
          for (int i = 0; i < 64; i++) {
            asm volatile("mov.b32 %0, %1;" : "=f"(s[i]) : "f"(ga[i]));
            asm volatile("mov.b32 %0, %1;" : "=f"(o[i]) : "f"(gb[i]));
          }
        } else {
          float ga[64], gb[64];
#pragma unroll
          for (int i = 0; i < 64; i++) {
            asm volatile("mov.b32 %0, %1;" : "=f"(ga[i]) : "f"(s[i]));
            asm volatile("mov.b32 %0, %1;" : "=f"(gb[i]) : "f"(o[i]));
          }
#pragma unroll 1
          for (int i = 0; i < nst; i++) {
            mbar_wait(gfull + (i & 3) * 8, (i >> 2) & 1);
            const uint64_t da = make_desc(base + unit_of(xt, i & 3) + wg * 8192, 16, 1024), db = make_desc(base + unit_of(wt, i & 3), 8192, 1024);
            if (i == nst - 1) bar_sync(2 + wg, 256);
            wg_fence();
#pragma unroll
            for (int kk = 0; kk < 4; kk++) mma256_ss(ga, gb, da + kk * 2, db + kk * 128, kk ? 1 : i);
            wg_commit();
            if (i == nst - 1) bar_arrive(3 - wg, 256);
            wg_wait<1>();
            mbar_arrive_cl(rempty, GE + ((i + 3) & 3) * 8, i != 0);
            PROF(4, tid == 0 && (i & 3) == 0, 40 + (ps - 1) * 4 + i / 4);
          }
          wg_wait<0>();
          keep(ga); keep(gb);
#pragma unroll
          for (int i = 0; i < 64; i++) {
            asm volatile("mov.b32 %0, %1;" : "=f"(s[i]) : "f"(ga[i]));
            asm volatile("mov.b32 %0, %1;" : "=f"(o[i]) : "f"(gb[i]));
          }
        }
        mbar_arrive_cl(rempty, GE + (ps == 2 ? 24 : 8));
        if (ps == 2) break;
      }
      const uint32_t qw = base + wg * 8192, qt = QT >> (16 * ps), at = ps ? AT1 : AT0;
      {
        const uint32_t wt = ps ? WT1 : WT0;
        const uint64_t da0 = make_desc(qw + unit_of(qt, 2), 16, 1024), da1 = make_desc(qw + unit_of(qt, 3), 16, 1024);
        const uint64_t db0 = make_desc(base + unit_of(wt, 2), 8192, 1024), db1 = make_desc(base + unit_of(wt, 3), 8192, 1024);
        mbar_wait(gfull + 16, 1);
        bar_sync(2 + wg, 256);
        wg_fence();
#pragma unroll
        for (int kk = 0; kk < 4; kk++) mma_ss<1>(s, da0 + kk * 2, db0 + kk * 128, 1);
        wg_commit();
        mbar_wait(xfull + 24, 1);
        mbar_wait(gfull + 24, 1);
        wg_fence();
#pragma unroll
        for (int kk = 0; kk < 4; kk++) mma_ss<1>(s, da1 + kk * 2, db1 + kk * 128, 1);
        wg_commit();
        bar_arrive(3 - wg, 256);
        mbar_wait(ps == 0 ? bar_pread : bar_ofree + 8, 0);
        wg_wait<0>();
        keep(s);
        PROF(2, tid == 0, 8 + ps * 8);
        uint32_t q[32];
        pack_p(s, q);
#pragma unroll
        for (int i = 0; i < 4; i++) stmatrix4((qw + unit_of(qt, 0) + frag_offset(warp)) ^ (i << 5), q[4 * i], q[4 * i + 1], q[4 * i + 2], q[4 * i + 3]);
        keep(q);
        bar_sync(2 + wg, 256);
        wg_fence();
#pragma unroll
        for (int kk = 0; kk < 8; kk++) mma_ss<1>(o, (kk < 4 ? da0 : da1) + (kk & 3) * 2, (kk < 4 ? db0 : db1) + UNIT / 16 + (kk & 3) * 128, 1);
        wg_commit();
        mbar_wait(bfull, 0);
        wg_fence();
        const uint64_t dk = make_desc(base + unit_of(at, 0), 16, 1024);
#pragma unroll
        for (int kk = 0; kk < 8; kk++) mma_rs<0>(s, q[4 * kk], q[4 * kk + 1], q[4 * kk + 2], q[4 * kk + 3], dk + (kk >> 2) * 1024 + (kk & 3) * 2, kk != 0);
        wg_commit();
        bar_arrive(3 - wg, 256);
#pragma unroll
        for (int i = 4; i < 8; i++) stmatrix4((qw + unit_of(qt, 1) + frag_offset(warp)) ^ ((i & 3) << 5), q[4 * i], q[4 * i + 1], q[4 * i + 2], q[4 * i + 3]);
        wg_wait<1>();
        keep(o);
        mbar_arrive_cl(rempty, GE + 16);
        mbar_arrive_cl(rempty, GE + 24);
        store_chunk<0>(o, qw + unit_of(qt, 2) + frag_offset(warp));
        store_chunk<1>(o, qw + unit_of(qt, 3) + frag_offset(warp));
        wg_wait<0>();
        keep(s);
        mbar_arrive_cl(rempty, 0);
      }
      PROF(4, tid == 0 && ps == 1, 61);
      float l0 = 0.f, l1 = 0.f;
      auto step = [&](auto odd_c, const int j, uint32_t (&pw)[32], uint32_t (&pr)[32]) {
        constexpr bool ODD = decltype(odd_c)::value;
        const bool first = !ODD && (j & 2) == 0, last = ODD && j == 7;
        const uint32_t ph = (j >> 1) & 1;
        float i0, i1, a0, a1;
        const bool so = !ODD && j == 4;
        if (so) { i0 = inv_quad_sum(l0); i1 = inv_quad_sum(l1); l0 = 0.f; l1 = 0.f; }
        bool redo = !ODD && (j | ps) == 0;
        while (true) {
          if (redo) {
            float m0 = fmaxf(s[0], s[1]), m1 = fmaxf(s[2], s[3]);
#pragma unroll
            for (int i = 1; i < 16; i++) { m0 = fmaxf(m0, fmaxf(s[4 * i], s[4 * i + 1])); m1 = fmaxf(m1, fmaxf(s[4 * i + 2], s[4 * i + 3])); }
            m0 = fmaxf(m0, __shfl_xor_sync(0xffffffffu, m0, 1)); m1 = fmaxf(m1, __shfl_xor_sync(0xffffffffu, m1, 1));
            m0 = fmaxf(m0, __shfl_xor_sync(0xffffffffu, m0, 2)); m1 = fmaxf(m1, __shfl_xor_sync(0xffffffffu, m1, 2));
            m0 *= SCL2; m1 *= SCL2;
            if (!first) {
              m0 = fmaxf(m0, f0); m1 = fmaxf(m1, f1);
              const float c0 = ex2(f0 - m0), c1 = ex2(f1 - m1);
              l0 *= c0; l1 *= c1;
              wg_wait<0>();
              keep(o);
#pragma unroll
              for (int i = 0; i < 16; i++) { o[4 * i] *= c0; o[4 * i + 1] *= c0; o[4 * i + 2] *= c1; o[4 * i + 3] *= c1; }
            }
            f0 = m0; f1 = m1;
          }
          float b0 = 0.f, b1 = 0.f;
          a0 = 0.f; a1 = 0.f;
#pragma unroll
          for (int i = 0; i < 16; i++) {
            const float e0 = ex2(fmaf(s[4 * i], SCL2, -f0)), e1 = ex2(fmaf(s[4 * i + 1], SCL2, -f0));
            const float e2 = ex2(fmaf(s[4 * i + 2], SCL2, -f1)), e3 = ex2(fmaf(s[4 * i + 3], SCL2, -f1));
            a0 += e0; b0 += e1; a1 += e2; b1 += e3;
            pw[2 * i] = pack_bf(e0, e1); pw[2 * i + 1] = pack_bf(e2, e3);
            if (i == VREL) {
#pragma unroll
              for (int k = 0; k < 2 * VREL + 2; k++) asm volatile("" : "+r"(pw[k])::"memory");
              mbar_wait(bar_mod, 0);
              wg_wait<0>();
              mbar_arrive_cl(rempty, ODD ? 16 : 0, !redo && (ODD || j));
#pragma unroll
              for (int k = 4 * VREL + 4; k < 64; k++) asm volatile("" : "+f"(s[k])::"memory");
            }
          }
          a0 += b0; a1 += b1;
          if (redo) break;
          redo = __any_sync(0xffffffffu, !(a0 + a1 < 0x1p90f));
          if (first) {
            uint32_t m0 = __ballot_sync(0xffffffffu, a0 > 0x1p-80f), m1 = __ballot_sync(0xffffffffu, a1 > 0x1p-80f);
            m0 |= m0 >> 1; m1 |= m1 >> 1; m0 |= m0 >> 2; m1 |= m1 >> 2;
            redo = redo || (m0 & m1 & 0x11111111u) != 0x11111111u;
          }
          if (!redo) break;
        }
        l0 += a0; l1 += a1;
        keep(pw);
        keep(o);
        if (so) store_chunk<0>(o, i0, i1, qw + unit_of(qt, 0) + frag_offset(warp));
        keep(o);
        if (j == (ODD ? 5 : 0)) { fence_async_smem(); if (ODD) mbar_arrive(bar_ofull + wg * 8); }
        mbar_wait(bfull + (ODD ? 24 : 8), ph);
        bar_sync(2 + wg, 256);
        if (!last) {
          const uint32_t qn = qt >> (j >= 3 ? 8 : 0);
          wg_fence();
          issue_qk(s, qw + unit_of(qn, 0), qw + unit_of(qn, 1), base + unit_of(at, ODD ? 3 : 1));
          wg_commit();
          mbar_wait(bfull + (ODD ? 0 : 16), ODD ? ph ^ 1 : ph);
        }
        if (so) { store_chunk<1>(o, i0, i1, qw + unit_of(qt, 1) + frag_offset(warp)); keep(o); }
        wg_fence();
        issue_pv(o, pw, base + unit_of(at, ODD ? (last ? 3 : 0) : 2), !first);
        wg_commit();
        bar_arrive(3 - wg, 256);
        wg_wait<1>();
        keep(s);
        mbar_arrive_cl(rempty, ODD ? 24 : 8, !last);
        PROF(4, tid == 0 && ps == 1, 51 + j);
      };
      uint32_t pa[32], pb[32];
#pragma unroll 1
      for (int j = 0; j < 8; j += 2) {
        step(std::false_type{}, j, pa, pb);
        step(std::true_type{}, j + 1, pb, pa);
      }
      {
        const float i0 = inv_quad_sum(l0), i1 = inv_quad_sum(l1);
        wg_wait<0>();
        keep(o);
        mbar_arrive_cl(rempty, 24);
        store_chunk<0>(o, i0, i1, qw + unit_of(qt, 2) + frag_offset(warp));
        store_chunk<1>(o, i0, i1, qw + unit_of(qt, 3) + frag_offset(warp));
        fence_async_smem();
        mbar_arrive(bar_ofull + 16 + wg * 8);
      }
      PROF(2, tid == 0, 10 + ps * 8);
    }

    const int ln = fresh_lane(), g = ln >> 2, tq = ln & 3, ct = warp * 32 + ln;
    const bool lane0 = ln == 0;
    const int lrow0 = warp * 16 + g;
    const int grow0 = rb * 128 + lrow0;
    const uint32_t res = base + OFF_RES, trow = res + wg * 8192 + frag_offset(warp);
    uint32_t xr[32];
    uint4 sv[4], own;
    uint32_t* sp[4];
#pragma unroll
    for (int k = 0; k < 4; k++) sp[k] = g_stats + ((((tq >> 1) * 4 + k) ^ cj) * SEQ + grow0 + (tq & 1) * 8) * 4;
    {
      const uint64_t da = make_desc(base + wg * 8192, 16, 1024), db = make_desc(base, 8192, 1024);
      constexpr int U = UNIT / 16;
#define HALF_STAGE(acc, xu, wu) _Pragma("unroll") for (int kk = 0; kk < 4; kk++) mma_ss<1>(acc, da + (xu) * U + kk * 2, db + (wu) * U + kk * 128, 1)
      PROF(10, ct == PT, 19); STAMP(0);
      cluster_arrive();
      mbar_wait(gfull, 1);
      mbar_wait(gfull + 8, 1);
      bar_sync(2 + wg, 256);
      wg_fence();
      HALF_STAGE(o, 7, 1);
      HALF_STAGE(o, 8, 3);
      wg_commit();
      STAMP(16);
      mbar_wait(gfull + 16, 1);
      STAMP(17);
      wg_fence();
      HALF_STAGE(o, 6, 11);
      wg_commit();
      bar_arrive(3 - wg, 256);
      mbar_wait(bar_par, 0);
      uint32_t* xo = g_xch + ((size_t)b * 8 * 256 + ct) * 4;
      const uint32_t* xi = g_xch + ((size_t)(b ^ 2) * 8 * 256 + ct) * 4;
      const uint32_t par1 = (~lds1(par + PAR_CONST + 4) & 1) << 16;
      wg_wait<1>();
      mbar_arrive_pred(bar_rel, lane0);
      wg_wait<0>();
      keep(o);
      mbar_arrive_pred(bar_ring, lane0);
      PROF(8, ct == PT, 20); STAMP(1);
#define SEND(i) st_b128(xo + (i) * 1024, (pack_bf(o[8 * (i)], o[8 * (i) + 1]) & ~0x10000u) | par1, pack_bf(o[8 * (i) + 2], o[8 * (i) + 3]), \
                        pack_bf(o[8 * (i) + 4], o[8 * (i) + 5]), pack_bf(o[8 * (i) + 6], o[8 * (i) + 7]))
#pragma unroll
      for (int i = 0; i < NS1; i++) SEND(i);
      PROF(8, ct == PT, 21); STAMP(2);
      bar_sync(2 + wg, 256);
      wg_fence();
      HALF_STAGE(s, 7, 0);
      HALF_STAGE(s, 8, 2);
      HALF_STAGE(s, 6, 10);
      wg_commit();
      bar_arrive(3 - wg, 256);
      STAMP(18);
      mbar_wait(gfull + 24, 1);
#pragma unroll
      for (int i = NS1; i < 8; i++) SEND(i);
      uint4 v[8];
#pragma unroll
      for (int i = 0; i < LD1; i++) v[i] = ld_b128(xi + i * 1024);
      STAMP(19);
      mbar_wait(bar_xres, 0);
      wg_wait<0>();
      mbar_arrive_pred(bar_ring + 8, lane0);
      bar_sync(2 + wg, 256);
      STAMP(20);
#pragma unroll
      for (int i = LD1; i < LD2; i++) v[i] = ld_b128(xi + i * 1024);
      mbar_wait(bar_xres, 0);
      wg_fence();
      HALF_STAGE(s, 9, 4);
      wg_commit();
      mbar_wait(bar_rx, 0);
      wg_fence();
      HALF_STAGE(s, 1, 5);
      wg_commit();
      bar_arrive(3 - wg, 256);
      STAMP(21);
#pragma unroll
      for (int i = LD2; i < 8; i++) v[i] = ld_b128(xi + i * 1024);
      if (LD2 < 8) mbar_wait(bar_xres, 0);
      wg_wait<0>();
      keep(s);
      mbar_arrive_pred(bar_ring + 16, lane0);
      PROF(10, ct == PT, 23); STAMP(4);
#pragma unroll
      for (int i = 0; i < 16; i += 2) ldmatrix4((trow ^ ((i & 7) << 4)) + (i >> 3) * 16384, xr[2 * i], xr[2 * i + 1], xr[2 * i + 2], xr[2 * i + 3]);
      uint32_t ga[16];
      uint4 bw[8];
#pragma unroll
      for (int i = 0; i < 8; i++) {
        if (!(i & 1)) {
          const uint4 t = lds4(par + PAR_SINK + i * 32 + tq * 16);
          ga[2 * i] = t.x; ga[2 * i + 1] = t.y; ga[2 * i + 2] = t.z; ga[2 * i + 3] = t.w;
        }
        bw[i] = lds4(par + PAR_T1 + i * 64 + tq * 16);
        if (!(g & 1)) { bw[i].x = 0x3f803f80u; bw[i].y = 0x3f803f80u; }
      }
      uint32_t pk[32];
      pack_p(s, pk);
      keep(pk);
      {
        uint32_t n = 0, miss;
        do {
          miss = 0;
#pragma unroll
          for (int i = 0; i < 8; i++) miss |= v[i].x ^ par1;
          miss = __any_sync(0xffffffffu, miss & 0x10000u);
          if (miss) {
#pragma unroll
            for (int i = 0; i < 8; i++)
              asm volatile("{ .reg .pred p; .reg .b32 t; xor.b32 t, %0, %5; and.b32 t, t, 0x10000; setp.ne.u32 p, t, 0;\n"
                           "@p ld.relaxed.gpu.global.v4.u32 {%0, %1, %2, %3}, [%4]; }"
                           : "+r"(v[i].x), "+r"(v[i].y), "+r"(v[i].z), "+r"(v[i].w) : "l"(xi + i * 1024), "r"(par1) : "memory");
          }
          watchdog(n);
        } while (miss);
      }
      PROF(8, ct == PT, 22); STAMP(3);
      float ds[4] = {0.f, 0.f, 0.f, 0.f}, dl[4] = {0.f, 0.f, 0.f, 0.f}, q0[4] = {0.f, 0.f, 0.f, 0.f}, q1[4] = {0.f, 0.f, 0.f, 0.f};
#pragma unroll
      for (int i = 0; i < 8; i++) {
        const uint32_t u0 = hfma2(ga[2 * i], hadd2(pk[4 * i], v[i].x & ~0x10000u), xr[4 * i]);
        const uint32_t u1 = hfma2(ga[2 * i], hadd2(pk[4 * i + 1], v[i].y), xr[4 * i + 1]);
        const uint32_t u2 = hfma2(ga[2 * i + 1], hadd2(pk[4 * i + 2], v[i].z), xr[4 * i + 2]);
        const uint32_t u3 = hfma2(ga[2 * i + 1], hadd2(pk[4 * i + 3], v[i].w), xr[4 * i + 3]);
        xr[4 * i] = u0; xr[4 * i + 1] = u1; xr[4 * i + 2] = u2; xr[4 * i + 3] = u3;
        mma16816(ds, u0, u1, u2, u3, bw[i].x, bw[i].y);
        mma16816(dl, u0, u1, u2, u3, bw[i].z, bw[i].w);
        mma16816(q0, u0, u1, u2, u3, u0, u2);
        mma16816(q1, u0, u1, u2, u3, u1, u3);
      }
      const float sqa = __shfl_sync(0xffffffffu, (g & 1) ? q0[1] : q0[0], g * 4 + (g >> 1));
      const float sqb = __shfl_sync(0xffffffffu, (g & 1) ? q1[3] : q1[2], g * 4 + (g >> 1));
      own = (tq & 1) ? make_uint4(__float_as_uint(ds[2]), __float_as_uint(sqb), __float_as_uint(ds[3] + dl[3]), tag)
                                 : make_uint4(__float_as_uint(ds[0]), __float_as_uint(sqa), __float_as_uint(ds[1] + dl[1]), tag);
      if (tq < 2) st_b128(sp[0], own.x, own.y, own.z, own.w);
#pragma unroll
      for (int k = 0; k < 4; k++) sv[k] = make_uint4(0, 0, 0, 0);
    }
    PROF(8, ct == PT, 29); STAMP(5);
    uint32_t mm, ih, il;
    float rbest;
    uint32_t wf[128];
    const uint32_t frow = (ln & 7) + (ln >> 4) * 8;
    const uint32_t wfo = base + (warp & 1) * 8192 + frow * 64 + ((((ln >> 3) & 1) ^ ((frow >> 1) & 3)) << 4);
#define LOAD_WF(m) _Pragma("unroll") for (int f = 0; f < 16; f++) {                                                   \
      const int r = ((f >> 1) * 4 + (m) * 2 + (f & 1)) * 4;                                                           \
      ldmatrix4t(((wfo + unit_of((m) ? FT_U : FT_G, warp >> 1)) ^ ((f & 1) * 32)) + (f >> 1) * 1024, wf[r], wf[r + 1], wf[r + 2], wf[r + 3]); \
    }
    bool early;
    {
#pragma unroll
      for (int i = 0; i < 16; i += 2) stmatrix4((trow ^ ((i & 7) << 4)) + (i >> 3) * 16384, xr[2 * i], xr[2 * i + 1], xr[2 * i + 2], xr[2 * i + 3]);
      const uint4 cst = lds4(par + PAR_CONST);
      const float A1 = __uint_as_float(cst.x), A2 = __uint_as_float(cst.z);
      uint32_t n = 0;
      early = false;
#pragma unroll 1
      while (true) {
        uint32_t miss;
        asm volatile("{ .reg .pred p0, p1, p2, p3; .reg .b64 u, v; .reg .b128 w;\n"
                     "setp.ge.u32 p0, %22, 2; setp.ne.and.u32 p0, %4, %21, p0; setp.ne.u32 p1, %8, %21; setp.ne.u32 p2, %12, %21; setp.ne.u32 p3, %16, %21;\n"
                     "@p0 ld.relaxed.gpu.global.v4.u32 {%1, %2, %3, %4}, [%17];\n"
                     "@p1 ld.relaxed.gpu.global.v4.u32 {%5, %6, %7, %8}, [%18];\n"
                     "@p2 ld.relaxed.gpu.global.v4.u32 {%9, %10, %11, %12}, [%19];\n"
                     "@p3 ld.relaxed.gpu.global.v4.u32 {%13, %14, %15, %16}, [%20];\n"
                     "or.pred p0, p0, p1; or.pred p2, p2, p3; or.pred p0, p0, p2; vote.sync.any.pred p0, p0, 0xffffffff; selp.u32 %0, 1, 0, p0; }"
                     : "=r"(miss), "+r"(sv[0].x), "+r"(sv[0].y), "+r"(sv[0].z), "+r"(sv[0].w), "+r"(sv[1].x), "+r"(sv[1].y), "+r"(sv[1].z), "+r"(sv[1].w),
                       "+r"(sv[2].x), "+r"(sv[2].y), "+r"(sv[2].z), "+r"(sv[2].w), "+r"(sv[3].x), "+r"(sv[3].y), "+r"(sv[3].z), "+r"(sv[3].w)
                     : "l"(sp[0]), "l"(sp[1]), "l"(sp[2]), "l"(sp[3]), "r"(tag), "r"(tq) : "memory");
        if (!miss) break;
        if (!early && (b >= NFFN || __all_sync(0xffffffffu, mbar_test(bar_box + (warp >> 1) * 8, 0)))) {
          early = true;
          LOAD_WF(0);
          __syncwarp();
          mbar_arrive_pred(bar_gate, lane0);
        }
        watchdog(n);
      }
      const uint4 v0 = tq < 2 ? own : sv[0], v1 = sv[1], v2 = sv[2], v3 = sv[3];
      PROF(8, ct == PT, 30); STAMP(6);
      float su = (__uint_as_float(v0.x) + __uint_as_float(v1.x)) + (__uint_as_float(v2.x) + __uint_as_float(v3.x));
      float sq = (__uint_as_float(v0.y) + __uint_as_float(v1.y)) + (__uint_as_float(v2.y) + __uint_as_float(v3.y));
      float dt = (__uint_as_float(v0.z) + __uint_as_float(v1.z)) + (__uint_as_float(v2.z) + __uint_as_float(v3.z));
      su += __shfl_xor_sync(0xffffffffu, su, 2); sq += __shfl_xor_sync(0xffffffffu, sq, 2); dt += __shfl_xor_sync(0xffffffffu, dt, 2);
      const float m = su * (1.f / DM);
      float mb, sd;
      ln_scalars(m, fmaxf(sq * (1.f / DM) - m * m, 0.f), mb, sd);
      const float inv = rcp(sd);
      rbest = (dt - mb * A1) * inv + A2;
      mm = pack_bf(mb, mb);
      ih = pack_bf(inv, inv);
      const float lo = inv - bf_lo(ih);
      il = pack_bf(lo, lo);
    }
    int ibest;
    {
      const uint32_t bits = __float_as_uint(rbest);
      const uint32_t key = (((int)bits < 0 ? ~bits : bits | 0x80000000u) & ~0x1ffu) | ((127 - lrow0 - (tq & 1) * 8) << 2) | tag;
      sts1(par + PAR_RED + warp * 4, __reduce_max_sync(0xffffffffu, key));
      PROF(8, ct == PT, 38); STAMP(7);
      bar_sync(1, 256);
      const uint4 ka = lds4(par + PAR_RED), kb = lds4(par + PAR_RED + 16);
      const uint32_t k2 = max(max(max(ka.x, ka.y), max(ka.z, ka.w)), max(max(kb.x, kb.y), max(kb.z, kb.w)));
      if (ct == 0 && cj == 0) st_relaxed(g_cand + rb, k2);
      ibest = 127 - ((k2 >> 2) & 127);
    }
    PROF(8, ct == PT, 39); STAMP(8);
    if ((ibest >> 4) == warp) {
      const int src = (ibest & 7) * 4 + ((ibest >> 3) & 1), ch = g * 2;
      const uint32_t cm = __shfl_sync(0xffffffffu, mm, src), ch_ = __shfl_sync(0xffffffffu, ih, src), cl = __shfl_sync(0xffffffffu, il, src);
      const uint32_t xa = res + (ch >> 3) * 16384 + ibest * 128 + (((ch & 7) ^ (ibest & 7)) << 4) + tq * 4;
      const uint32_t x0 = lds1(xa), x1 = lds1(xa ^ 16);
      const uint2 p0 = lds2(par + PAR_T2 + ch * 64 + tq * 16), p1 = lds2(par + PAR_T2 + ch * 64 + 64 + tq * 16);
      uint32_t* dst = g_row + rb * 2 * DM + cj * 128 + ln * 4;
      st_pairs(dst, ln_mod(x0, cm, ch_, cl, p0.x, p0.y), ln_mod(x1, cm, ch_, cl, p1.x, p1.y), tag);
      st_pairs(dst + DM, x0, x1, tag);
      __syncwarp();
    }
    PROF(8, ct == PT, 37); STAMP(9);
    uint32_t wd[64];
    const uint32_t wda = base + unit_of(FT_D, warp >> 1) + (warp & 1) * 8192 + frow * 128 + ((((ln >> 3) & 1) ^ (ln & 7)) << 4);
#define LOAD_WD(f) ldmatrix4t((wda ^ ((((f) >> 1) & 3) * 32)) + ((f) >> 3) * 4096 + ((f) & 1) * 2048, wd[4 * (f)], wd[4 * (f) + 1], wd[4 * (f) + 2], wd[4 * (f) + 3])
    if (!early) {
      if (b < NFFN) mbar_wait(bar_box + (warp >> 1) * 8, 0);
      LOAD_WF(0);
      __syncwarp();
      mbar_arrive_pred(bar_gate, lane0);
    }
    if (b < NFFN) {
      const uint32_t own = base + unit_of(FT_G, warp >> 1) + (warp & 1) * 8192;
      mbar_wait(bar_box + (4 + (warp >> 1)) * 8, 0);
      LOAD_WF(1);
      uint32_t* const ydst = g_ypart + ((size_t)(warp * 16 + tq * 2) * NFFN + b) * 8 + g;
      PROF(8, ct == PT, 31); STAMP(10);
      bool wdok;
      {
        uint32_t n = 0;
        while (!(wdok = __all_sync(0xffffffffu, mbar_test(bar_box + (8 + (warp >> 1)) * 8, 0))) && !__all_sync(0xffffffffu, mbar_test(bar_sel, 0))) watchdog(n);
      }
      if (wdok) {
#pragma unroll
        for (int f = 0; f < 16; f++) LOAD_WD(f);
      }
      STAMP(11);
      mbar_wait(bar_sel, 0);
      PROF(8, ct == PT, 33); STAMP(12);
      float d[8][4];
#pragma unroll
      for (int i = 0; i < 4; i++) { d[i][0] = 0.f; d[i][1] = 0.f; d[i][2] = 0.f; d[i][3] = 0.f; }
#pragma unroll
      for (int ks = 0; ks < 8; ks++) {
        const uint2 hb = lds2(own + 256 + ks * 32 + tq * 8);
#pragma unroll
        for (int mt = 0; mt < 4; mt++) {
          const int r = ks * 16 + mt * 4;
          mma16816(d[mt], wf[r], wf[r + 1], wf[r + 2], wf[r + 3], hb.x, hb.y);
        }
      }
      sts2(own + (tq * 8 + g) * 8, __float_as_uint((tq & 2) ? ((tq & 1) ? d[1][2] : d[1][0]) : ((tq & 1) ? d[0][2] : d[0][0])),
           __float_as_uint((tq & 2) ? ((tq & 1) ? d[3][2] : d[3][0]) : ((tq & 1) ? d[2][2] : d[2][0])));
      bar_sync(1, 256);
      uint32_t ab[4];
      {
        float G = 0.f, U = 0.f;
        uint2 pv[8];
#pragma unroll
        for (int w8 = 0; w8 < 8; w8++) pv[w8] = lds2(base + ln * 8 + ((FT_G >> (w8 >> 1) * 4) & 15) * UNIT + (w8 & 1) * 8192);
#pragma unroll
        for (int w8 = 0; w8 < 8; w8 += 2) {
          G += __uint_as_float(pv[w8].x) + __uint_as_float(pv[w8 + 1].x);
          U += __uint_as_float(pv[w8].y) + __uint_as_float(pv[w8 + 1].y);
        }
        const float act = rbf(silu_f(rbf(G))) * rbf(U);
        const uint32_t pk = pack_bf(act, __shfl_down_sync(0xffffffffu, act, 1));
#pragma unroll
        for (int i = 0; i < 4; i++) ab[i] = __shfl_sync(0xffffffffu, pk, i * 8 + tq * 2);
      }
      if (!wdok) {
        mbar_wait(bar_box + (8 + (warp >> 1)) * 8, 0);
#pragma unroll
        for (int f = 0; f < 16; f++) LOAD_WD(f);
      }
      PROF(8, ct == PT, 34); STAMP(13);
#pragma unroll
      for (int mt = 0; mt < 8; mt++) {
        d[mt][0] = 0.f; d[mt][1] = 0.f; d[mt][2] = 0.f; d[mt][3] = 0.f;
        mma16816(d[mt], wd[mt * 8], wd[mt * 8 + 1], wd[mt * 8 + 2], wd[mt * 8 + 3], ab[0], ab[1]);
        mma16816(d[mt], wd[mt * 8 + 4], wd[mt * 8 + 5], wd[mt * 8 + 6], wd[mt * 8 + 7], ab[2], ab[3]);
      }
#pragma unroll
      for (int i = 0; i < 4; i++) {
        const int m4 = (i >> 1) * 4, e = (i & 1) * 2;
        const float y = (tq & 2) ? ((tq & 1) ? d[m4 + 3][e] : d[m4 + 2][e]) : ((tq & 1) ? d[m4 + 1][e] : d[m4][e]);
        st_relaxed(ydst + (m4 * 2 + (i & 1)) * NFFN * 8, tagf(y, tag));
      }
      PROF(8, ct == PT, 35); STAMP(14);
    }
    mbar_wait(bar_sel, 0);
    mbar_arrive_pred(bar_win, ct == 0);
    const int iwin = lds1(par + PAR_CONST + 60) & 0x7ff;
    const bool cand = (iwin >> 4) == rb * 8 + warp;
    {
      const uint32_t mm0 = __shfl_sync(0xffffffffu, mm, ln & ~1), mm1 = __shfl_sync(0xffffffffu, mm, ln | 1);
      const uint32_t ih0 = __shfl_sync(0xffffffffu, ih, ln & ~1), ih1 = __shfl_sync(0xffffffffu, ih, ln | 1);
      const uint32_t il0 = __shfl_sync(0xffffffffu, il, ln & ~1), il1 = __shfl_sync(0xffffffffu, il, ln | 1);
#pragma unroll 1
      for (int hf = 0; hf < 2; hf++) {
        uint32_t x[16];
#pragma unroll
        for (int i = 0; i < 8; i += 2) ldmatrix4((trow ^ (i << 4)) + hf * 16384, x[2 * i], x[2 * i + 1], x[2 * i + 2], x[2 * i + 3]);
#pragma unroll
        for (int i = 0; i < 8; i++) {
          const uint4 pv = lds4(par + PAR_T2 + (hf * 8 + i) * 64 + tq * 16);
          x[2 * i] = hadd2(x[2 * i], hmul2(pv.z, ln_mod(x[2 * i], mm0, ih0, il0, pv.x, pv.y)));
          x[2 * i + 1] = hadd2(x[2 * i + 1], hmul2(pv.z, ln_mod(x[2 * i + 1], mm1, ih1, il1, pv.x, pv.y)));
        }
#pragma unroll
        for (int i = 0; i < 8; i += 2) stmatrix4((trow ^ (i << 4)) + hf * 16384, x[2 * i], x[2 * i + 1], x[2 * i + 2], x[2 * i + 3]);
      }
      if (!cand) fence_async_smem();
      __syncwarp();
      if (!cand && elect_one()) {
        tma2d_store(&maps.out, res + warp * 2048, cj * 128, rb * 128 + warp * 16);
        tma2d_store(&maps.out, res + 16384 + warp * 2048, cj * 128 + 64, rb * 128 + warp * 16);
        asm volatile("cp.async.bulk.commit_group;" ::: "memory");
      }
    }
    if (cand) {
      const int wrow0 = warp * 16;
#pragma unroll 2
      for (int p = 0; p < 8; p++) {
        const int row = 2 * p + (ln >> 4), ch = ln & 15;
        const uint4 v = lds4(res + (ch >> 3) * 16384 + (wrow0 + row) * 128 + (((ch & 7) ^ (row & 7)) << 4));
        if (rb * 128 + wrow0 + row != iwin) *reinterpret_cast<uint4*>(P.out + (size_t)(rb * 128 + wrow0 + row) * DM + cj * 128 + ch * 8) = v;
      }
    }
    asm volatile("cp.async.bulk.wait_group.read 0;" ::: "memory");
    PROF(8, ct == PT, 11); STAMP(15);
    cluster_wait();
  }
}

typedef CUresult (*EncodeFn)(CUtensorMap*, CUtensorMapDataType, cuuint32_t, void*, const cuuint64_t*, const cuuint64_t*,
                             const cuuint32_t*, const cuuint32_t*, CUtensorMapInterleave, CUtensorMapSwizzle,
                             CUtensorMapL2promotion, CUtensorMapFloatOOBfill);

void map2d(EncodeFn enc, CUtensorMap* m, const void* p, uint64_t rows, uint64_t cols, uint32_t brows) {
  cuuint64_t dims[2] = {cols, rows}, strides[1] = {cols * 2};
  cuuint32_t box[2] = {64, brows}, es[2] = {1, 1};
  enc(m, CU_TENSOR_MAP_DATA_TYPE_BFLOAT16, 2, const_cast<void*>(p), dims, strides, box, es, CU_TENSOR_MAP_INTERLEAVE_NONE,
      CU_TENSOR_MAP_SWIZZLE_128B, CU_TENSOR_MAP_L2_PROMOTION_L2_256B, CU_TENSOR_MAP_FLOAT_OOB_FILL_NONE);
}
void map2d_narrow(EncodeFn enc, CUtensorMap* m, const void* p, uint64_t rows, uint64_t cols, uint32_t brows) {
  cuuint64_t dims[2] = {cols, rows}, strides[1] = {cols * 2};
  cuuint32_t box[2] = {32, brows}, es[2] = {1, 1};
  enc(m, CU_TENSOR_MAP_DATA_TYPE_BFLOAT16, 2, const_cast<void*>(p), dims, strides, box, es, CU_TENSOR_MAP_INTERLEAVE_NONE,
      CU_TENSOR_MAP_SWIZZLE_64B, CU_TENSOR_MAP_L2_PROMOTION_L2_64B, CU_TENSOR_MAP_FLOAT_OOB_FILL_NONE);
}
void map3d(EncodeFn enc, CUtensorMap* m, const void* p, uint64_t rows, uint64_t cols, uint32_t brows, uint32_t nch) {
  cuuint64_t dims[3] = {64, rows, cols / 64}, strides[2] = {cols * 2, 128};
  cuuint32_t box[3] = {64, brows, nch}, es[3] = {1, 1, 1};
  enc(m, CU_TENSOR_MAP_DATA_TYPE_BFLOAT16, 3, const_cast<void*>(p), dims, strides, box, es, CU_TENSOR_MAP_INTERLEAVE_NONE,
      CU_TENSOR_MAP_SWIZZLE_128B, CU_TENSOR_MAP_L2_PROMOTION_L2_256B, CU_TENSOR_MAP_FLOAT_OOB_FILL_NONE);
}

}

extern "C" void kernel_launch(void* const* d_in, const int* in_sizes, int n_in, void* d_out, int out_size) {
  (void)in_sizes; (void)n_in; (void)out_size;
  static EncodeFn enc = nullptr;
  if (!enc) {
    void* fn = nullptr;
    cudaDriverEntryPointQueryResult st;
    cudaGetDriverEntryPoint("cuTensorMapEncodeTiled", &fn, cudaEnableDefault, &st);
    enc = (EncodeFn)fn;
    cudaFuncSetAttribute(fused_kernel, cudaFuncAttributeMaxDynamicSharedMemorySize, SMEM_BYTES);
  }
  Maps maps;
  map2d(enc, &maps.x, d_in[0], SEQ, DM, 128);
  map2d(enc, &maps.out, d_out, SEQ, DM, 16);
  map3d(enc, &maps.wq, d_in[3], DM, NQ, 64, 2);
  map3d(enc, &maps.k, d_in[1], 4 * SK, 128, 128, 1);
  map3d(enc, &maps.v, d_in[2], 4 * SK, 128, 128, 1);
  map3d(enc, &maps.wo, d_in[4], NQ, DM, 64, 2);
  map2d_narrow(enc, &maps.wg, d_in[7], DM, FF, 256);
  map2d_narrow(enc, &maps.wu, d_in[8], DM, FF, 256);
  map3d(enc, &maps.wd, d_in[9], FF, DM, 32, 4);
  map2d_narrow(enc, &maps.wm, d_in[11], DM, NMOD, 256);
  Ptrs p;
  p.x = (const __nv_bfloat16*)d_in[0];
  p.w_r = (const __nv_bfloat16*)d_in[6];
  p.w_gate = (const __nv_bfloat16*)d_in[7];
  p.w_up = (const __nv_bfloat16*)d_in[8];
  p.w_down = (const __nv_bfloat16*)d_in[9];
  p.c = (const __nv_bfloat16*)d_in[10];
  p.w_mod = (const __nv_bfloat16*)d_in[11];
  p.out = (__nv_bfloat16*)d_out;
  fused_kernel<<<NMAIN + NHELP, 384, SMEM_BYTES>>>(maps, p);
}
```

```cpp
#include <cuda_runtime.h>
#include <cuda_bf16.h>
#include <cuda.h>
#include <stdint.h>
#include <type_traits>

#define HD 2
#define HDX 2
#define NRS 8
#define FPACE 3
#define GOST 20
#define WB 2
#define WN 20
#define RES0 17
#define RES1 20
#define HU 32
#define NS1 5
#define PG0 15
#define PSL 0
#define FB0 0
#define FB2 8
#define OPS 8192
#define OFL 0
#define ODS 8
#define MODUL hfma2
#define ODS1 5
#define LD1 0
#define LD2 4
#define FB1 2
#define FPB 8
#define FPACE0 2
#define VREL 5
#define E0 3

namespace {

constexpr int SEQ = 2048, DM = 1024, NQ = 4096, SK = 2048, WIN = 512, FF = 3584, NMOD = 6144;
constexpr int NMAIN = 128, NHELP = 4, NFFN = 112;
constexpr int NSLOT = 4, SLOT_BYTES = 32768, UNIT = 16384, GST_BYTES = 3 * UNIT;
constexpr uint32_t XT1 = 0xDCBA, XT2 = 0x9687;
constexpr uint32_t WT0 = 0xA741, WT1 = 0x7420, WT2 = 0x4A20;
constexpr uint32_t AT0 = WT1, AT1 = WT2;
constexpr uint32_t QT = 0xDC9696DC;
constexpr int OFF_STAGE = 12 * UNIT;
constexpr uint32_t FT_G = 0x07B3, FT_U = 0xA628, FT_D = 0x5149;
constexpr int OFF_RES = 12 * UNIT;
constexpr int OFF_PAR = 14 * UNIT;
constexpr int OFF_BAR = OFF_PAR + 2528;
constexpr int SMEM_BYTES = OFF_BAR + 544;
static_assert(SMEM_BYTES <= 232448, "smem");

constexpr int PAR_T1 = 0;
constexpr int PAR_T2 = 512;
constexpr int PAR_CONST = 1536;
constexpr int PAR_RED = 1600;
constexpr int PAR_SINK = 2176;

struct Maps {
  CUtensorMap x, wq, k, v, wo, wg, wu, wd, wm, out;
};
struct Ptrs {
  const __nv_bfloat16 *x, *w_r, *c, *w_mod, *w_gate, *w_up, *w_down;
  __nv_bfloat16* out;
};

__device__ __align__(1024) uint8_t g_act[16 * 80 * UNIT];
__device__ __align__(128) uint32_t g_mod[NMOD];
__device__ __align__(128) uint32_t g_modp[2 * 2 * DM];
__device__ __align__(128) uint32_t g_ln1[SEQ * 4];
__device__ __align__(128) uint32_t g_cnt_h[16 * 32];
__device__ __align__(128) uint32_t g_cnt_o[128 * 32];
__device__ __align__(128) uint32_t g_xch[NMAIN * 8 * 256 * 4];
__device__ __align__(128) uint32_t g_stats[8 * SEQ * 4];
__device__ __align__(128) uint32_t g_cand[32];
__device__ __align__(128) uint32_t g_row[16 * 2 * DM];
__device__ __align__(128) uint32_t g_ypart[NMAIN * NFFN * 8];
__device__ uint32_t g_epoch;

__device__ __forceinline__ uint32_t fresh_lane() { uint32_t l; asm volatile("mov.u32 %0, %%laneid;" : "=r"(l)); return l; }
__device__ __forceinline__ uint32_t frag_offset(int warp) {
  const uint32_t l = fresh_lane();
  return ((warp & 3) * 16 + (l & 15)) * 128 + (((l >> 4) ^ (l & 7)) << 4);
}
__device__ __forceinline__ bool elect_one() {
  uint32_t p;
  asm volatile("{ .reg .pred q; elect.sync _|q, 0xffffffff; selp.u32 %0, 1, 0, q; }" : "=r"(p));
  return p;
}
__device__ __forceinline__ uint32_t smem_u32(const void* p) { return (uint32_t)__cvta_generic_to_shared(p); }
__device__ __forceinline__ void mbar_init(uint32_t bar, uint32_t cnt) {
  asm volatile("mbarrier.init.shared::cta.b64 [%0], %1;" ::"r"(bar), "r"(cnt) : "memory");
}
__device__ __forceinline__ void mbar_expect_tx(uint32_t bar, uint32_t bytes) {
  asm volatile("mbarrier.arrive.expect_tx.shared::cta.b64 _, [%0], %1;" ::"r"(bar), "r"(bytes) : "memory");
}
__device__ __forceinline__ void mbar_arrive(uint32_t bar) {
  asm volatile("mbarrier.arrive.shared::cta.b64 _, [%0];" ::"r"(bar) : "memory");
}
__device__ __forceinline__ void mbar_arrive_pred(uint32_t bar, bool p) {
  asm volatile("{ .reg .pred p; setp.ne.b32 p, %1, 0; @p mbarrier.arrive.shared::cta.b64 _, [%0]; }" ::"r"(bar), "r"((int)p) : "memory");
}
__device__ __forceinline__ void mbar_arrive_cl(uint32_t bar, uint32_t off, bool p = true) {
  asm volatile("{ .reg .pred p, q; .reg .b32 a; setp.ne.b32 q, %2, 0; setp.ne.and.b32 p, %0, 0, q; add.u32 a, %0, %1; @p mbarrier.arrive.shared::cluster.b64 _, [a]; }"
               ::"r"(bar), "r"(off), "r"((int)p) : "memory");
}
__device__ __forceinline__ uint32_t mapa(uint32_t addr, uint32_t cta) {
  uint32_t r; asm("mapa.shared::cluster.u32 %0, %1, %2;" : "=r"(r) : "r"(addr), "r"(cta)); return r;
}
__device__ __forceinline__ void cluster_arrive() { asm volatile("barrier.cluster.arrive.relaxed.aligned;" ::: "memory"); }
__device__ __forceinline__ void cluster_wait() { asm volatile("barrier.cluster.wait.aligned;" ::: "memory"); }
__device__ __forceinline__ void watchdog(uint32_t& n) {
}
__device__ __forceinline__ void mbar_wait(uint32_t bar, uint32_t parity) {
  asm volatile("{\n.reg .pred p;\nWAIT_%=:\nmbarrier.try_wait.parity.shared::cta.b64 p, [%0], %1;\n@!p bra WAIT_%=;\n}" ::"r"(bar), "r"(parity) : "memory");
}
__device__ __forceinline__ bool mbar_test(uint32_t bar, uint32_t parity) {
  uint32_t ok;
  asm volatile("{\n.reg .pred p;\nmbarrier.test_wait.parity.shared::cta.b64 p, [%1], %2;\nselp.u32 %0, 1, 0, p;\n}" : "=r"(ok) : "r"(bar), "r"(parity) : "memory");
  return ok;
}
__device__ __forceinline__ uint64_t l2_stream() {
  uint64_t f; asm("createpolicy.fractional.L2::evict_first.b64 %0, 1.0;" : "=l"(f)); return f;
}
__device__ __forceinline__ void tma2d(uint32_t dst, const CUtensorMap* m, int c0, int c1, uint32_t bar) {
  asm volatile("cp.async.bulk.tensor.2d.shared::cluster.global.mbarrier::complete_tx::bytes.L2::cache_hint [%0], [%1, {%3, %4}], [%2], %5;"
               ::"r"(dst), "l"(m), "r"(bar), "r"(c0), "r"(c1), "l"(l2_stream()) : "memory");
}
__device__ __forceinline__ void bulk_load(uint32_t dst, const void* src, uint32_t bytes, uint32_t bar) {
  asm volatile("cp.async.bulk.shared::cluster.global.mbarrier::complete_tx::bytes [%0], [%1], %2, [%3];" ::"r"(dst), "l"(src), "r"(bytes), "r"(bar) : "memory");
}
__device__ __forceinline__ void bulk_load_stream(uint32_t dst, const void* src, uint32_t bytes, uint32_t bar) {
  asm volatile("cp.async.bulk.shared::cluster.global.mbarrier::complete_tx::bytes.L2::cache_hint [%0], [%1], %2, [%3], %4;"
               ::"r"(dst), "l"(src), "r"(bytes), "r"(bar), "l"(l2_stream()) : "memory");
}
__device__ __forceinline__ void tma2d_store(const CUtensorMap* m, uint32_t src, int c0, int c1) {
  asm volatile("cp.async.bulk.tensor.2d.global.shared::cta.bulk_group [%0, {%2, %3}], [%1];" ::"l"(m), "r"(src), "r"(c0), "r"(c1) : "memory");
}
__device__ __forceinline__ void bulk_store(void* dst, uint32_t src, uint32_t bytes) {
  asm volatile("cp.async.bulk.global.shared::cta.bulk_group [%0], [%1], %2;" ::"l"(dst), "r"(src), "r"(bytes) : "memory");
}
__device__ __forceinline__ int slice_of(int i) { return i + ((i & 7) == 1) - ((i & 7) == 2); }
__device__ __forceinline__ uint32_t unit_of(uint32_t table, uint32_t i) { return ((table >> (i * 4)) & 15) * UNIT; }
__device__ __forceinline__ void tma3d(uint32_t dst, const CUtensorMap* m, int c0, int c1, int c2, uint32_t bar) {
  asm volatile("cp.async.bulk.tensor.3d.shared::cluster.global.mbarrier::complete_tx::bytes.L2::cache_hint [%0], [%1, {%3, %4, %5}], [%2], %6;"
               ::"r"(dst), "l"(m), "r"(bar), "r"(c0), "r"(c1), "r"(c2), "l"(l2_stream()) : "memory");
}
template <bool STREAM>
__device__ __forceinline__ void tma3d_mc(uint32_t dst, const CUtensorMap* m, int c0, int c1, int c2, uint32_t bar) {
  if (STREAM)
    asm volatile("cp.async.bulk.tensor.3d.shared::cluster.global.mbarrier::complete_tx::bytes.multicast::cluster.L2::cache_hint [%0], [%1, {%3, %4, %5}], [%2], %6, %7;"
                 ::"r"(dst), "l"(m), "r"(bar), "r"(c0), "r"(c1), "r"(c2), "h"((uint16_t)3), "l"(l2_stream()) : "memory");
  else
    asm volatile("cp.async.bulk.tensor.3d.shared::cluster.global.mbarrier::complete_tx::bytes.multicast::cluster [%0], [%1, {%3, %4, %5}], [%2], %6;"
                 ::"r"(dst), "l"(m), "r"(bar), "r"(c0), "r"(c1), "r"(c2), "h"((uint16_t)3) : "memory");
}
__device__ __forceinline__ void prefetch_map(const CUtensorMap* m) {
  asm volatile("prefetch.tensormap [%0];" ::"l"(m) : "memory");
}
__device__ __forceinline__ void fence_async() { asm volatile("fence.proxy.async.global;" ::: "memory"); }
__device__ __forceinline__ void fence_async_smem() { asm volatile("fence.proxy.async.shared::cta;" ::: "memory"); }
__device__ __forceinline__ void bar_sync(int id, int n) { asm volatile("bar.sync %0, %1;" ::"r"(id), "r"(n) : "memory"); }
__device__ __forceinline__ void bar_arrive(int id, int n) { asm volatile("bar.arrive %0, %1;" ::"r"(id), "r"(n) : "memory"); }
__device__ __forceinline__ void wg_fence() { asm volatile("wgmma.fence.sync.aligned;" ::: "memory"); }
__device__ __forceinline__ void wg_commit() { asm volatile("wgmma.commit_group.sync.aligned;" ::: "memory"); }
template <int N> __device__ __forceinline__ void wg_wait() { asm volatile("wgmma.wait_group.sync.aligned %0;" ::"n"(N) : "memory"); }
__device__ __forceinline__ uint64_t make_desc(uint32_t addr, uint32_t lbo, uint32_t sbo) {
  return (uint64_t)((addr & 0x3FFFF) >> 4) | ((uint64_t)(lbo >> 4) << 16) | ((uint64_t)(sbo >> 4) << 32) | (1ull << 62);
}
__device__ __forceinline__ uint32_t ld_relaxed(const uint32_t* p) {
  uint32_t v; asm volatile("ld.relaxed.gpu.global.u32 %0, [%1];" : "=r"(v) : "l"(p) : "memory"); return v;
}
__device__ __forceinline__ uint32_t ld_acquire(const uint32_t* p) {
  uint32_t v; asm volatile("ld.acquire.gpu.global.u32 %0, [%1];" : "=r"(v) : "l"(p) : "memory"); return v;
}
__device__ __forceinline__ uint4 ld_relaxed4(const uint32_t* p) {
  uint4 v; asm volatile("ld.relaxed.gpu.global.v4.u32 {%0,%1,%2,%3}, [%4];" : "=r"(v.x), "=r"(v.y), "=r"(v.z), "=r"(v.w) : "l"(p) : "memory"); return v;
}
__device__ __forceinline__ uint2 ld_relaxed2(const uint32_t* p) {
  uint2 v; asm volatile("ld.relaxed.gpu.global.v2.u32 {%0,%1}, [%2];" : "=r"(v.x), "=r"(v.y) : "l"(p) : "memory"); return v;
}
__device__ __forceinline__ void st_relaxed(uint32_t* p, uint32_t v) {
  asm volatile("st.relaxed.gpu.global.u32 [%0], %1;" ::"l"(p), "r"(v) : "memory");
}
__device__ __forceinline__ void st_relaxed2(uint32_t* p, uint32_t a, uint32_t b) {
  asm volatile("st.relaxed.gpu.global.v2.u32 [%0], {%1,%2};" ::"l"(p), "r"(a), "r"(b) : "memory");
}
__device__ __forceinline__ void st_relaxed4(uint32_t* p, uint32_t a, uint32_t b, uint32_t c, uint32_t d) {
  asm volatile("st.relaxed.gpu.global.v4.u32 [%0], {%1,%2,%3,%4};" ::"l"(p), "r"(a), "r"(b), "r"(c), "r"(d) : "memory");
}
__device__ __forceinline__ void st_b128(uint32_t* p, uint32_t a, uint32_t b, uint32_t c, uint32_t d) {
  asm volatile("{ .reg .b64 u, v; .reg .b128 w; mov.b64 u, {%1, %2}; mov.b64 v, {%3, %4}; mov.b128 w, {u, v}; st.relaxed.gpu.global.b128 [%0], w; }"
               ::"l"(p), "r"(a), "r"(b), "r"(c), "r"(d) : "memory");
}
__device__ __forceinline__ uint4 ld_b128(const uint32_t* p) {
  uint4 r;
  asm volatile("{ .reg .b64 u, v; .reg .b128 w; ld.relaxed.gpu.global.b128 w, [%4]; mov.b128 {u, v}, w; mov.b64 {%0, %1}, u; mov.b64 {%2, %3}, v; }"
               : "=r"(r.x), "=r"(r.y), "=r"(r.z), "=r"(r.w) : "l"(p) : "memory");
  return r;
}
__device__ __forceinline__ void st_pairs(uint32_t* p, uint32_t a, uint32_t b, uint32_t tag) {
  asm volatile("{ .reg .b64 u, v; mov.b64 u, {%1, %3}; mov.b64 v, {%2, %3}; st.relaxed.gpu.global.v2.b64 [%0], {u, v}; }"
               ::"l"(p), "r"(a), "r"(b), "r"(tag) : "memory");
}
__device__ __forceinline__ uint4 ld_pairs(const uint32_t* p) {
  uint4 v;
  asm volatile("{ .reg .b64 u, v; ld.relaxed.gpu.global.v2.b64 {u, v}, [%4]; mov.b64 {%0, %1}, u; mov.b64 {%2, %3}, v; }"
               : "=r"(v.x), "=r"(v.y), "=r"(v.z), "=r"(v.w) : "l"(p) : "memory");
  return v;
}
__device__ __forceinline__ uint2 ld_pair(const uint32_t* p) {
  uint2 v;
  asm volatile("{ .reg .b64 u; ld.relaxed.gpu.global.b64 u, [%2]; mov.b64 {%0, %1}, u; }" : "=r"(v.x), "=r"(v.y) : "l"(p) : "memory");
  return v;
}
__device__ __forceinline__ void red_release(uint32_t* p, uint32_t v) {
  asm volatile("red.release.gpu.global.add.u32 [%0], %1;" ::"l"(p), "r"(v) : "memory");
}
__device__ __forceinline__ uint32_t ldg_nc1(const void* p) {
  uint32_t v;
  asm volatile("ld.global.nc.u32 %0, [%1];" : "=r"(v) : "l"(p));
  return v;
}
__device__ __forceinline__ uint4 ldg_nc4(const void* p) {
  uint4 v; asm volatile("ld.global.nc.L1::no_allocate.v4.u32 {%0,%1,%2,%3}, [%4];" : "=r"(v.x), "=r"(v.y), "=r"(v.z), "=r"(v.w) : "l"(p)); return v;
}
__device__ __forceinline__ uint4 ldg_stream4(const void* p) {
  uint4 v;
  asm volatile("ld.global.nc.L1::no_allocate.L2::cache_hint.v4.u32 {%0,%1,%2,%3}, [%4], %5;" : "=r"(v.x), "=r"(v.y), "=r"(v.z), "=r"(v.w) : "l"(p), "l"(l2_stream()));
  return v;
}
__device__ __forceinline__ void stg4(void* p, uint4 v) {
  asm volatile("st.global.v4.u32 [%0], {%1,%2,%3,%4};" ::"l"(p), "r"(v.x), "r"(v.y), "r"(v.z), "r"(v.w) : "memory");
}
__device__ __forceinline__ void wait_counter(const uint32_t* p, uint32_t target) {
  uint32_t n = 0;
  while (__any_sync(0xffffffffu, (int)(ld_acquire(p) - target) < 0)) { watchdog(n); }
}
__device__ __forceinline__ uint32_t tagf(float v, uint32_t tag) { return (__float_as_uint(v) & ~3u) | tag; }
__device__ __forceinline__ bool tag_ok(uint4 v, uint32_t tag) { return (((v.x ^ tag) | (v.y ^ tag) | (v.z ^ tag) | (v.w ^ tag)) & 3u) == 0; }
__device__ __forceinline__ float untag_sum(uint32_t a, uint32_t b) { return __uint_as_float(a & ~3u) + __uint_as_float(b & ~3u); }
__device__ __forceinline__ uint4 poll4(const uint32_t* p, uint32_t tag) {
  uint4 v = ld_relaxed4(p);
  uint32_t n = 0;
  while (!__all_sync(0xffffffffu, tag_ok(v, tag))) { v = ld_relaxed4(p); watchdog(n); }
  return v;
}
__device__ __forceinline__ float bf_lo(uint32_t v) { return __uint_as_float(v << 16); }
__device__ __forceinline__ float bf_hi(uint32_t v) { return __uint_as_float(v & 0xffff0000u); }
__device__ __forceinline__ uint32_t pack_bf(float lo, float hi) {
  uint32_t r; asm("cvt.rn.bf16x2.f32 %0, %1, %2;" : "=r"(r) : "f"(hi), "f"(lo)); return r;
}
__device__ __forceinline__ float rbf(float v) { return __uint_as_float(pack_bf(0.f, v) & 0xffff0000u); }
__device__ __forceinline__ uint32_t hmul2(uint32_t a, uint32_t b) {
  uint32_t r; asm("mul.rn.bf16x2 %0, %1, %2;" : "=r"(r) : "r"(a), "r"(b)); return r;
}
__device__ __forceinline__ uint32_t hadd2(uint32_t a, uint32_t b) {
  uint32_t r; asm("add.rn.bf16x2 %0, %1, %2;" : "=r"(r) : "r"(a), "r"(b)); return r;
}
__device__ __forceinline__ uint32_t hsub2(uint32_t a, uint32_t b) {
  uint32_t r; asm("sub.rn.bf16x2 %0, %1, %2;" : "=r"(r) : "r"(a), "r"(b)); return r;
}
__device__ __forceinline__ uint32_t hmax2(uint32_t a, uint32_t b) {
  uint32_t r; asm("max.bf16x2 %0, %1, %2;" : "=r"(r) : "r"(a), "r"(b)); return r;
}
__device__ __forceinline__ float rcp(float x) { float r; asm("rcp.approx.ftz.f32 %0, %1;" : "=f"(r) : "f"(x)); return r; }
__device__ __forceinline__ float ex2(float x) { float r; asm("ex2.approx.ftz.f32 %0, %1;" : "=f"(r) : "f"(x)); return r; }
__device__ __forceinline__ void stmatrix4(uint32_t addr, uint32_t a, uint32_t b, uint32_t c, uint32_t d) {
  asm volatile("stmatrix.sync.aligned.m8n8.x4.shared.b16 [%0], {%1,%2,%3,%4};" ::"r"(addr), "r"(a), "r"(b), "r"(c), "r"(d) : "memory");
}
__device__ __forceinline__ void ldmatrix4(uint32_t addr, uint32_t& a, uint32_t& b, uint32_t& c, uint32_t& d) {
  asm volatile("ldmatrix.sync.aligned.m8n8.x4.shared.b16 {%0,%1,%2,%3}, [%4];" : "=r"(a), "=r"(b), "=r"(c), "=r"(d) : "r"(addr) : "memory");
}
__device__ __forceinline__ void ldmatrix4t(uint32_t addr, uint32_t& a, uint32_t& b, uint32_t& c, uint32_t& d) {
  asm volatile("ldmatrix.sync.aligned.m8n8.x4.trans.shared.b16 {%0,%1,%2,%3}, [%4];" : "=r"(a), "=r"(b), "=r"(c), "=r"(d) : "r"(addr) : "memory");
}
__device__ __forceinline__ void mma16816(float (&d)[4], uint32_t a0, uint32_t a1, uint32_t a2, uint32_t a3, uint32_t b0, uint32_t b1) {
  asm volatile("mma.sync.aligned.m16n8k16.row.col.f32.bf16.bf16.f32 {%0,%1,%2,%3}, {%4,%5,%6,%7}, {%8,%9}, {%0,%1,%2,%3};"
               : "+f"(d[0]), "+f"(d[1]), "+f"(d[2]), "+f"(d[3]) : "r"(a0), "r"(a1), "r"(a2), "r"(a3), "r"(b0), "r"(b1));
}
__device__ __forceinline__ void sts1(uint32_t a, uint32_t v) { asm volatile("st.shared.u32 [%0], %1;" ::"r"(a), "r"(v) : "memory"); }
__device__ __forceinline__ uint4 lds4(uint32_t a) {
  uint4 v; asm volatile("ld.shared.v4.u32 {%0,%1,%2,%3}, [%4];" : "=r"(v.x), "=r"(v.y), "=r"(v.z), "=r"(v.w) : "r"(a) : "memory"); return v;
}
__device__ __forceinline__ uint2 lds2(uint32_t a) {
  uint2 v; asm volatile("ld.shared.v2.u32 {%0,%1}, [%2];" : "=r"(v.x), "=r"(v.y) : "r"(a) : "memory"); return v;
}
__device__ __forceinline__ uint32_t lds1(uint32_t a) {
  uint32_t v; asm volatile("ld.shared.u32 %0, [%1];" : "=r"(v) : "r"(a) : "memory"); return v;
}
__device__ __forceinline__ void sts2(uint32_t a, uint32_t x, uint32_t y) { asm volatile("st.shared.v2.u32 [%0], {%1,%2};" ::"r"(a), "r"(x), "r"(y) : "memory"); }
__device__ __forceinline__ void sts4(uint32_t a, uint4 v) {
  asm volatile("st.shared.v4.u32 [%0], {%1,%2,%3,%4};" ::"r"(a), "r"(v.x), "r"(v.y), "r"(v.z), "r"(v.w) : "memory");
}
__device__ __forceinline__ float silu_f(float v) { return __fdividef(v, 1.f + __expf(-v)); }
__device__ __forceinline__ uint32_t hfma2(uint32_t a, uint32_t b, uint32_t c) {
  uint32_t r; asm("fma.rn.bf16x2 %0, %1, %2, %3;" : "=r"(r) : "r"(a), "r"(b), "r"(c)); return r;
}
__device__ __forceinline__ void split_inv(float sd, uint32_t& ih, uint32_t& il) {
  const float inv = rcp(sd);
  ih = pack_bf(inv, inv);
  const float lo = inv - bf_lo(ih);
  il = pack_bf(lo, lo);
}
__device__ __forceinline__ uint32_t ln_norm(uint32_t x, uint32_t mean2, uint32_t ih, uint32_t il) {
  const uint32_t d = hsub2(x, mean2);
  return hfma2(d, ih, hmul2(d, il));
}
__device__ __forceinline__ uint32_t modul(uint32_t n, uint32_t c1, uint32_t sh) { return hadd2(hmul2(n, c1), sh); }
__device__ __forceinline__ uint32_t ln_mod(uint32_t x, uint32_t mean2, uint32_t ih, uint32_t il, uint32_t c1, uint32_t sh) {
  return modul(ln_norm(x, mean2, ih, il), c1, sh);
}

#define R8(a, i) "+f"(a[i]), "+f"(a[i + 1]), "+f"(a[i + 2]), "+f"(a[i + 3]), "+f"(a[i + 4]), "+f"(a[i + 5]), "+f"(a[i + 6]), "+f"(a[i + 7])
#define D64 "{%0,%1,%2,%3,%4,%5,%6,%7,%8,%9,%10,%11,%12,%13,%14,%15,%16,%17,%18,%19,%20,%21,%22,%23,%24,%25,%26,%27,%28,%29,%30,%31," \
            "%32,%33,%34,%35,%36,%37,%38,%39,%40,%41,%42,%43,%44,%45,%46,%47,%48,%49,%50,%51,%52,%53,%54,%55,%56,%57,%58,%59,%60,%61,%62,%63}"
template <int TB>
__device__ __forceinline__ void mma_ss(float (&d)[64], uint64_t da, uint64_t db, int sc) {
  asm volatile("{\n.reg .pred p;\nsetp.ne.b32 p, %66, 0;\n"
               "wgmma.mma_async.sync.aligned.m64n128k16.f32.bf16.bf16 " D64 ", %64, %65, p, 1, 1, 0, %67;\n}"
               : R8(d, 0), R8(d, 8), R8(d, 16), R8(d, 24), R8(d, 32), R8(d, 40), R8(d, 48), R8(d, 56)
               : "l"(da), "l"(db), "r"(sc), "n"(TB));
}
template <int TB>
__device__ __forceinline__ void mma_rs(float (&d)[64], uint32_t a0, uint32_t a1, uint32_t a2, uint32_t a3, uint64_t db, int sc) {
  asm volatile("{\n.reg .pred p;\nsetp.ne.b32 p, %69, 0;\n"
               "wgmma.mma_async.sync.aligned.m64n128k16.f32.bf16.bf16 " D64 ", {%64,%65,%66,%67}, %68, p, 1, 1, %70;\n}"
               : R8(d, 0), R8(d, 8), R8(d, 16), R8(d, 24), R8(d, 32), R8(d, 40), R8(d, 48), R8(d, 56)
               : "r"(a0), "r"(a1), "r"(a2), "r"(a3), "l"(db), "r"(sc), "n"(TB));
}
#define D128 "{%0,%1,%2,%3,%4,%5,%6,%7,%8,%9,%10,%11,%12,%13,%14,%15,%16,%17,%18,%19,%20,%21,%22,%23,%24,%25,%26,%27,%28,%29,%30,%31," \
             "%32,%33,%34,%35,%36,%37,%38,%39,%40,%41,%42,%43,%44,%45,%46,%47,%48,%49,%50,%51,%52,%53,%54,%55,%56,%57,%58,%59,%60,%61,%62,%63," \
             "%64,%65,%66,%67,%68,%69,%70,%71,%72,%73,%74,%75,%76,%77,%78,%79,%80,%81,%82,%83,%84,%85,%86,%87,%88,%89,%90,%91,%92,%93,%94,%95," \
             "%96,%97,%98,%99,%100,%101,%102,%103,%104,%105,%106,%107,%108,%109,%110,%111,%112,%113,%114,%115,%116,%117,%118,%119,%120,%121,%122,%123,%124,%125,%126,%127}"
#define R128(d, e) R8(d, 0), R8(d, 8), R8(d, 16), R8(d, 24), R8(d, 32), R8(d, 40), R8(d, 48), R8(d, 56), \
                   R8(e, 0), R8(e, 8), R8(e, 16), R8(e, 24), R8(e, 32), R8(e, 40), R8(e, 48), R8(e, 56)
__device__ __forceinline__ void mma256_ss(float (&d)[64], float (&e)[64], uint64_t da, uint64_t db, int sc) {
  asm volatile("{\n.reg .pred p;\nsetp.ne.b32 p, %130, 0;\n"
               "wgmma.mma_async.sync.aligned.m64n256k16.f32.bf16.bf16 " D128 ", %128, %129, p, 1, 1, 0, 1;\n}"
               : R128(d, e) : "l"(da), "l"(db), "r"(sc));
}
__device__ __forceinline__ void mma256_rs(float (&d)[64], float (&e)[64], uint32_t a0, uint32_t a1, uint32_t a2, uint32_t a3, uint64_t db) {
  asm volatile("{\n.reg .pred p;\nsetp.ne.b32 p, 1, 0;\n"
               "wgmma.mma_async.sync.aligned.m64n256k16.f32.bf16.bf16 " D128 ", {%128,%129,%130,%131}, %132, p, 1, 1, 1;\n}"
               : R128(d, e) : "r"(a0), "r"(a1), "r"(a2), "r"(a3), "l"(db));
}
template <int N> __device__ __forceinline__ void keep(float (&a)[N]) {
#pragma unroll
  for (int i = 0; i < N; i++) asm volatile("" : "+f"(a[i])::"memory");
}
template <int N> __device__ __forceinline__ void keep(uint32_t (&a)[N]) {
#pragma unroll
  for (int i = 0; i < N; i++) asm volatile("" : "+r"(a[i])::"memory");
}

#define STAMP(idx) do {} while (0)
#define PROF(grp, cond, idx) do {} while (0)

constexpr float SCL2 = 1.4426950408889634f * 0.08838834764831845f;

__device__ __forceinline__ void pack_p(const float (&s)[64], uint32_t (&p)[32]) {
#pragma unroll
  for (int i = 0; i < 32; i++) p[i] = pack_bf(s[2 * i], s[2 * i + 1]);
}

__device__ __forceinline__ void issue_qk(float (&s)[64], uint32_t q0, uint32_t q1, uint32_t kslot) {
  const uint64_t db = make_desc(kslot, 16, 1024), da0 = make_desc(q0, 16, 1024), da1 = make_desc(q1, 16, 1024);
#pragma unroll
  for (int kk = 0; kk < 8; kk++) mma_ss<0>(s, (kk < 4 ? da0 : da1) + (kk & 3) * 2, db + (kk >> 2) * 1024 + (kk & 3) * 2, kk != 0);
}
__device__ __forceinline__ void issue_pv(float (&o)[64], uint32_t (&p)[32], uint32_t vslot, int acc) {
  uint64_t db = make_desc(vslot, 16384, 1024);
#pragma unroll
  for (int kk = 0; kk < 8; kk++)
    mma_rs<1>(o, p[4 * kk], p[4 * kk + 1], p[4 * kk + 2], p[4 * kk + 3], db + kk * 128, kk == 0 ? acc : 1);
}

template <int H>
__device__ __forceinline__ void store_chunk(const float (&a)[64], uint32_t addr) {
#pragma unroll
  for (int i = 8 * H; i < 8 * H + 8; i += 2)
    stmatrix4(addr ^ ((i & 7) << 4), pack_bf(a[4 * i], a[4 * i + 1]), pack_bf(a[4 * i + 2], a[4 * i + 3]),
              pack_bf(a[4 * i + 4], a[4 * i + 5]), pack_bf(a[4 * i + 6], a[4 * i + 7]));
}
template <int H>
__device__ __forceinline__ void store_chunk(const float (&a)[64], float i0, float i1, uint32_t addr) {
#pragma unroll
  for (int i = 8 * H; i < 8 * H + 8; i += 2)
    stmatrix4(addr ^ ((i & 7) << 4), pack_bf(a[4 * i] * i0, a[4 * i + 1] * i0), pack_bf(a[4 * i + 2] * i1, a[4 * i + 3] * i1),
              pack_bf(a[4 * i + 4] * i0, a[4 * i + 5] * i0), pack_bf(a[4 * i + 6] * i1, a[4 * i + 7] * i1));
}
__device__ __forceinline__ float inv_quad_sum(float l) {
  l += __shfl_xor_sync(0xffffffffu, l, 1);
  l += __shfl_xor_sync(0xffffffffu, l, 2);
  return rcp(l);
}

__device__ __forceinline__ void write_table(uint32_t table, bool ca, uint32_t t, const uint4& m0, const uint4& m1) {
  float c0 = untag_sum(m0.x, m1.x), c1 = untag_sum(m0.y, m1.y), c2 = untag_sum(m0.z, m1.z), c3 = untag_sum(m0.w, m1.w);
  if (ca) { c0 = 1.f + rbf(c0); c1 = 1.f + rbf(c1); c2 = 1.f + rbf(c2); c3 = 1.f + rbf(c3); }
  const uint32_t d = table + (t >> 2) * 64 + (t & 1) * 32 + (t & 2) * 2 + (ca ? 0 : 8);
  sts1(d, pack_bf(c0, c1));
  sts1(d + 16, pack_bf(c2, c3));
}

__device__ __forceinline__ void ln_scalars(float mean, float var, float& mb, float& sd) {
  mb = rbf(mean);
  float r; asm("sqrt.approx.ftz.f32 %0, %1;" : "=f"(r) : "f"(rbf(rbf(var) + 1e-5f)));
  sd = rbf(r);
}

__global__ void __cluster_dims__(2, 1, 1) __launch_bounds__(384, 1) fused_kernel(const __grid_constant__ Maps maps, const Ptrs P) {
  extern __shared__ __align__(1024) uint8_t smem_raw[];
  const uint32_t base = smem_u32(smem_raw);
  const int tid = threadIdx.x, lane = tid & 31;
  const int warp = __shfl_sync(0xffffffffu, tid >> 5, 0);
  const int b = blockIdx.x;
  PROF(31, tid == 0, 0);

  if (b >= NMAIN) {
    float* sc = reinterpret_cast<float*>(smem_raw);
    float* red = sc + DM;
    for (int k = tid; k < DM; k += 384) sc[k] = rbf(silu_f(__bfloat162float(P.c[k])));
    __syncthreads();
    if (tid < 256) {
      const int col = 2048 + (b - NMAIN) * 1024 + (tid & 127) * 8, r0 = (tid >> 7) * 512;
      float acc[8];
#pragma unroll
      for (int e = 0; e < 8; e++) acc[e] = 0.f;
#pragma unroll 1
      for (int r = r0; r < r0 + 512; r += HU) {
        uint4 w[HU];
#pragma unroll
        for (int u = 0; u < HU; u++) w[u] = ldg_stream4(P.w_mod + (size_t)(r + u) * NMOD + col);
#pragma unroll
        for (int u = 0; u < HU; u++) {
          float s = sc[r + u];
          acc[0] += s * bf_lo(w[u].x); acc[1] += s * bf_hi(w[u].x); acc[2] += s * bf_lo(w[u].y); acc[3] += s * bf_hi(w[u].y);
          acc[4] += s * bf_lo(w[u].z); acc[5] += s * bf_hi(w[u].z); acc[6] += s * bf_lo(w[u].w); acc[7] += s * bf_hi(w[u].w);
        }
      }
      if (tid >= 128) {
#pragma unroll
        for (int e = 0; e < 8; e++) red[(tid & 127) * 8 + e] = acc[e];
      }
      const uint32_t tag = ld_relaxed(&g_epoch) % 3 + 1;
      bar_sync(1, 256);
      if (tid < 128) {
        uint32_t o[8];
#pragma unroll
        for (int e = 0; e < 8; e++) o[e] = __float_as_uint(rbf(acc[e] + red[tid * 8 + e])) | tag;
        st_relaxed4(g_mod + col, o[0], o[1], o[2], o[3]);
        st_relaxed4(g_mod + col + 4, o[4], o[5], o[6], o[7]);
        const uint4 wr = ldg_nc4(P.w_r + tid * 8);
        const uint32_t wv[4] = {wr.x, wr.y, wr.z, wr.w};
        float dsum = 0.f;
#pragma unroll
        for (int e = 0; e < 8; e++) {
          const float m = bf_hi(o[e]);
          dsum += (b == NMAIN + 2 ? rbf(1.f + m) : m) * ((e & 1) ? bf_hi(wv[e >> 1]) : bf_lo(wv[e >> 1]));
        }
#pragma unroll
        for (int k = 16; k > 0; k >>= 1) dsum += __shfl_xor_sync(0xffffffffu, dsum, k);
        if (lane == 0) st_relaxed(g_mod + (b - NMAIN) * 4 + warp, tagf(dsum, tag));
      }
    }
    PROF(2, tid == 0, 1);
    return;
  }

  const int rank = b & 1;
  const int rb = ((b >> 4) << 1) | rank, cj = (b >> 1) & 7;
  const bool late = b & 4;
  const uint32_t bfull = base + OFF_BAR, bempty = bfull + NSLOT * 8;
  const uint32_t gfull = bempty + NSLOT * 8, gempty = gfull + 32;
  const uint32_t bar_ofull = gempty + 32;
  const uint32_t bar_ofree = bar_ofull + 32;
  const uint32_t bar_par = bar_ofree + 32;
  const uint32_t bar_mod = bar_par + 8;
  const uint32_t bar_pread = bar_mod + 8;
  const uint32_t bar_xres = bar_pread + 8;
  const uint32_t bar_ring = bar_xres + 8;
  const uint32_t bar_box = bar_ring + 24;
  const uint32_t bar_go = bar_box + 96;
  const uint32_t bar_go2 = bar_go + 16;
  const uint32_t bar_cnt = bar_go + 24;
  const uint32_t xfull = bar_go + 40, xempty = xfull + 32;
  const uint32_t bar_hw = xempty + 32, bar_hx = bar_hw + 8;
  const uint32_t bar_hpub = bar_hx + 16;
  const uint32_t bar_win = bar_hpub + 16;
  const uint32_t bar_rx = bar_win + 8;
  const uint32_t bar_sel = bar_rx + 8;
  const uint32_t bar_gate = bar_sel + 8;
  const uint32_t bar_rel = bar_gate + 8;
  const uint32_t bar_od = bar_rel + 8;
  const uint32_t bar_mod2 = bar_od + 8;
  const uint32_t bar_res = bar_go + 8;
  const uint32_t stage = base + OFF_STAGE, par = base + OFF_PAR;

  if (warp == 8 && elect_one()) {
    for (int s = 0; s < NSLOT; s++) { mbar_init(bfull + s * 8, 1); mbar_init(bempty + s * 8, 16); }
    for (int s = 0; s < 4; s++) { mbar_init(gfull + s * 8, 1); mbar_init(gempty + s * 8, 16); mbar_init(xfull + s * 8, 1); mbar_init(xempty + s * 8, 8); mbar_init(bar_ofree + s * 8, 1); mbar_init(bar_ofull + s * 8, 128); }
    mbar_init(bar_par, 64); mbar_init(bar_mod, 256); mbar_init(bar_pread, 2); mbar_init(bar_xres, 1);
    mbar_init(bar_ring, 8); mbar_init(bar_ring + 8, 8); mbar_init(bar_ring + 16, 8);
    mbar_init(bar_go, 1); mbar_init(bar_go2, 1); mbar_init(bar_cnt, 1); mbar_init(bar_cnt + 8, 1); mbar_init(bar_hpub, 8); mbar_init(bar_hpub + 8, 8); mbar_init(bar_res, 1); mbar_init(bar_win, 1); mbar_init(bar_rx, 1); mbar_init(bar_sel, 64); mbar_init(bar_gate, 8); mbar_init(bar_rel, 8); mbar_init(bar_od, 1); mbar_init(bar_mod2, 64);
    for (int s = 0; s < 12; s++) mbar_init(bar_box + s * 8, 1);
    asm volatile("fence.mbarrier_init.release.cluster;" ::: "memory");
    prefetch_map(&maps.x); prefetch_map(&maps.wq); prefetch_map(&maps.k); prefetch_map(&maps.v);
  }
  if (warp == 9 && elect_one()) {
    mbar_init(bar_hw, 1); mbar_init(bar_hx, 1); mbar_init(bar_hx + 8, 1);
    asm volatile("fence.mbarrier_init.release.cluster;" ::: "memory");
    mbar_expect_tx(bar_hw, 32768);
    mbar_expect_tx(bar_hx, 16384);
    mbar_expect_tx(bar_hx + 8, 16384);
    const __nv_bfloat16* xs = P.x + (size_t)(rb * 128 + cj * 16) * DM;
    bulk_load(base + 2 * GST_BYTES, xs, 16384, bar_hx);
    if (!late) {
      tma2d(stage, &maps.wm, (b >> 1) * 32, rank * 512, bar_hw);
      tma2d(stage + 16384, &maps.wm, (b >> 1) * 32, rank * 512 + 256, bar_hw);
    } else {
      prefetch_map(&maps.wm);
    }
    bulk_load(base + 3 * GST_BYTES, xs + 8 * DM, 16384, bar_hx + 8);
  }
  cluster_arrive();

  if (warp >= 8) {
    asm volatile("setmaxnreg.dec.sync.aligned.u32 40;");
    if (warp < 10) bar_arrive(1, 320);
    const uint32_t epoch = ld_relaxed(&g_epoch);
    cluster_wait();
    if (warp == 8) {
      const int kvrow = (cj >> 1) * SK + (SK - WIN);
      int wch = cj * 8 + rank * 2;
#pragma unroll 1
      for (int ps = 0; ps < 3; ps++) {
        const CUtensorMap* mw = ps == 2 ? &maps.wo : &maps.wq;
        const uint32_t xt = ps == 1 ? XT1 : XT2, wt = ps == 0 ? WT0 : (ps == 1 ? WT1 : WT2);
        const int nst = ps == 2 ? 32 : 16;
#pragma unroll 1
        for (int i = 0; i < nst; i++) {
          const uint32_t bf = gfull + (i & 3) * 8;
          const int kt = ps == 2 ? (((cj & 1) * 4 + ((i >> 1) & 3)) * 4 + (i >> 3)) * 2 + (i & 1) : (ps ? i : slice_of(i) + (b & 14)) & 15;
          const uint32_t wd = base + unit_of(wt, i & 3) + rank * UNIT, xd = base + unit_of(xt, i & 3);
          const uint8_t* xs = g_act + (uint32_t)(rb * 80 + (ps - 1) * 16 + kt) * UNIT;
          if (ps == 0 && i == HD) mbar_wait(bar_mod, 0);
          const bool xfirst = ps && i < 2;
          if (ps == 2 && i == 0) mbar_wait(bar_ofree + 24, 0);
          if (i == 0) fence_async();
          mbar_wait(gempty + (i & 3) * 8, ((i >> 2) & 1) ^ 1);
          if (elect_one()) {
            mbar_expect_tx(bf, ps ? GST_BYTES : 2 * UNIT);
            if (xfirst) bulk_load_stream(xd, xs, UNIT, bf);
          }
          if (ps && i < 4) mbar_wait(bempty + i * 8, 1);
          if (elect_one()) tma3d_mc<true>(wd, mw, 0, (i == 31 ? kt ^ (rank * 32) : kt) * 64, i == 31 ? cj * 2 : wch, bf);
          if (ps) {
            if (i == 16 || i == 24) { mbar_wait(bar_cnt + i - 16, 0); fence_async(); }
            if (i == RES0) mbar_wait(bar_res, 0);
            if (i == 2) mbar_wait(bar_ofree + (ps - 1) * 16, 0);
            if (elect_one()) {
              if (i == 31) bulk_load(xd, xs, UNIT, bf); else if (!xfirst) bulk_load_stream(xd, xs, UNIT, bf);
              mbar_arrive_pred(bar_go, i == GOST - 1);
              if (PG0 < 16) mbar_arrive_pred(bar_go2, ps == 1 && i == PG0);
              mbar_arrive_pred(bar_od, i == (ps == 1 ? ODS1 : ODS));
              if (i == RES0) mbar_expect_tx(bar_xres, 32768);
              if (i == RES0 || i == RES1) tma2d(base + OFF_RES + (i == RES1) * UNIT, &maps.x, cj * 128 + (i == RES1) * 64, rb * 128, bar_xres);
            }
          }
        }
        if (ps == 2) break;
        wch = ps ? ((wch >> 3) ^ rank) * 2 : wch + 4;
#pragma unroll 1
        for (int u = 0; u < 16; u++) {
          const bool isk = (u == 0) || ((u & 1) && u < 15);
          const int blk = (isk ? (u + 1) >> 1 : (u == 15 ? 7 : (u >> 1) - 1)) & 3;
          const uint32_t sl = base + unit_of(ps ? AT1 : AT0, u & 3) + rank * UNIT, bf = bfull + (u & 3) * 8;
          if (u < 4) mbar_wait(gempty + ((u + 1) >> 1) * 8, 1);
          mbar_wait(bempty + (u & 3) * 8, ((u >> 2) & 1) ^ 1);
          if (elect_one()) {
            mbar_arrive_pred(bar_go2, ps && u + 16 == PG0);
            mbar_expect_tx(bf, SLOT_BYTES);
            tma3d_mc<false>(sl, isk ? &maps.k : &maps.v, 0, kvrow + blk * 128, rank, bf);
          }
        }
      }
      if (elect_one()) mbar_expect_tx(bar_rx, UNIT);
      mbar_wait(bar_rel, 0);
      if (elect_one()) {
        bulk_load_stream(base + UNIT, g_act + (uint32_t)(rb * 80 + 16 + 63 - (cj & 1) * 32) * UNIT, UNIT, bar_rx);
      }
      if (b < NFFN) {
#pragma unroll 1
        for (int u = 0; u < 12; u++) {
          const uint32_t dst = base + unit_of(u < 4 ? FT_G : (u < 8 ? FT_U : FT_D), u & 3);
          if (elect_one()) mbar_expect_tx(bar_box + u * 8, UNIT);
          if (u == FB0 || u == FB1 || u == FB2) mbar_wait(bar_ring + (u == FB2 ? 16 : u == FB1 ? 8 : 0), 0);
          const int fp = u < FPB ? FPACE0 : FPACE;
          if (u >= fp) mbar_wait(bar_box + (u - fp) * 8, 0);
          if (elect_one()) {
            if (u < 8) tma2d(dst, u < 4 ? &maps.wg : &maps.wu, b * 32, (u & 3) * 256, bar_box + u * 8);
            else tma3d(dst, &maps.wd, 0, b * 32, (u - 8) * 4, bar_box + u * 8);
          }
        }
      }
    } else if (warp == 9) {
      const uint32_t target = 8 * (epoch + 1);
      uint32_t hmask = 0;
#pragma unroll 1
      for (int i = 0; i < 16; i++) {
        if (i == HDX) mbar_wait(bar_mod, 0);
        const int kt = (2 * cj + slice_of(i)) & 15;
        const uint32_t need = i == 15 ? 0xffffu : 1u << kt;
        if (i >= NRS && (hmask & need) != need) {
          uint32_t n = 0;
          do { hmask = __ballot_sync(0xffffffffu, ld_acquire(&g_cnt_h[rb * 32 + (lane & 15)]) == epoch + 1); watchdog(n); } while ((hmask & need) != need);
          PROF(1, lane == 0 && i == NRS, 26);
          fence_async();
        }
        mbar_wait(xempty + (i & 3) * 8, ((i >> 2) & 1) ^ 1);
        if (elect_one()) {
          mbar_expect_tx(xfull + (i & 3) * 8, UNIT);
          if (i < NRS) tma2d(base + (i & 3) * GST_BYTES, &maps.x, kt * 64, rb * 128, xfull + (i & 3) * 8);
          else bulk_load_stream(base + (i & 3) * GST_BYTES, g_act + (uint32_t)(rb * 80 + kt) * UNIT, UNIT, xfull + (i & 3) * 8);
        }
      }
      prefetch_map(&maps.wo);
#pragma unroll 1
      for (int t = 0; t < 4; t++) {
        if (t & 1) mbar_wait(bar_od, t >> 1);
#pragma unroll 1
        for (int p = 0; p < 32768 / OPS; p++) {
          const uint32_t w = p / (16384 / OPS), c = (p / (8192 / OPS)) & 1, off = w * 8192 + (p % (8192 / OPS)) * OPS;
          mbar_wait(bar_ofull + (t & 1) * 16 + w * 8, t >> 1);
          if (elect_one()) {
            bulk_store(g_act + (uint32_t)(rb * 80 + 16 + (cj * 4 + t) * 2 + c) * UNIT + off, base + unit_of(QT, 2 * t + c) + off, OPS);
            asm volatile("cp.async.bulk.commit_group;" ::: "memory");
            asm volatile("cp.async.bulk.wait_group.read %0;" ::"n"(OFL) : "memory");
          }
        }
        if (elect_one()) {
          asm volatile("cp.async.bulk.wait_group.read 0;" ::: "memory");
          mbar_arrive(t < 3 ? bar_ofree + t * 8 : bar_res);
          asm volatile("cp.async.bulk.wait_group 0;" ::: "memory");
          fence_async();
          red_release(&g_cnt_o[((rb * 4 + t) * 2 + (cj >> 2)) * 32], 2);
        }
        if (t) {
          wait_counter(&g_cnt_o[(rb * 8 + 2 * t + (cj & 1)) * 32], target);
          if (t & 1) wait_counter(&g_cnt_o[(rb * 8 + (t == 1 ? cj & 1 : 7 - (cj & 1))) * 32], target);
          if (elect_one()) mbar_arrive(t == 1 ? bar_ofree + 24 : bar_cnt + t * 8 - 16);
        }
      }
      PROF(2, lane == 0, 27);
      const uint32_t tag = epoch % 3 + 1;
      const uint32_t* inbox = g_cand + (lane & 15);
      mbar_wait(bar_ring + 16, 0);
      uint32_t c0 = ld_relaxed(inbox), n = 0;
#define CAND_STEP(cv)                                                                                        \
      {                                                                                                      \
        const bool valid = (cv & 3u) == tag, all = __all_sync(0xffffffffu, valid);                           \
        const uint32_t best = __reduce_max_sync(0xffffffffu, valid ? cv : 0u);                               \
        const uint32_t blk = __ffs(__ballot_sync(0xffffffffu, cv == best)) - 1;                              \
        if (best) sts2(par + PAR_CONST + 56, best, (blk << 7 | (~best >> 2 & 127)) | (all ? 0x1800 : 0x800)); \
        if (all) break;                                                                                      \
        cv = ld_relaxed(inbox);                                                                              \
      }
      while (true) { CAND_STEP(c0) watchdog(n); }
    } else {
      const int t2 = tid - 320;
      if (late && warp == 10) {
        mbar_wait(bar_hx, 0);
        if (elect_one()) {
          tma2d(stage, &maps.wm, (b >> 1) * 32, rank * 512, bar_hw);
          tma2d(stage + 16384, &maps.wm, (b >> 1) * 32, rank * 512 + 256, bar_hw);
        }
      }
      {
        const uint32_t tag = epoch % 3 + 1;
        mbar_wait(bar_hx + 8, 0);
        mbar_wait(bar_hw, 0);
        {
          const uint32_t t7 = (warp & 1) * 64 + (lane >> 4) * 32 + 16 + (lane & 15);
          const uint32_t* pm = g_modp + ((cj * 128 + t7 * 4) & (DM - 1));
          uint4 m0, m1, m2, m3;
          uint32_t n = 0;
          do {
            m0 = ld_relaxed4(pm); m1 = ld_relaxed4(pm + 2 * DM); m2 = ld_relaxed4(pm + DM); m3 = ld_relaxed4(pm + 3 * DM);
            watchdog(n);
          } while (!__all_sync(0xffffffffu, tag_ok(m0, tag) && tag_ok(m1, tag) && tag_ok(m2, tag) && tag_ok(m3, tag)));
          write_table(par, false, t7, m0, m1);
          write_table(par, true, t7, m2, m3);
          mbar_arrive(bar_mod2);
        }
      }
      mbar_wait(bar_hpub + (warp & 1) * 8, 0);
      PROF(1, t2 == 0, 24);
#pragma unroll 1
      for (int c = 0; c < 8; c++) {
        const uint32_t off = (warp & 1) * UNIT + c * 2048 + lane * 16;
        uint8_t* dst = g_act + (uint32_t)(rb * 80 + cj * 2) * UNIT + off;
        const uint4 v0 = lds4(stage + off), v1 = lds4(stage + off + 512), v2 = lds4(stage + off + 1024), v3 = lds4(stage + off + 1536);
        stg4(dst, v0); stg4(dst + 512, v1); stg4(dst + 1024, v2); stg4(dst + 1536, v3);
      }
      __syncwarp();
      PROF(1, t2 == 0, 15);
      if (lane == 0) {
        mbar_arrive(bar_pread);
        red_release(&g_cnt_h[rb * 32 + cj * 2 + (warp & 1)], 1);
        PROF(1, t2 == 0, 25);
        prefetch_map(&maps.wg); prefetch_map(&maps.wu); prefetch_map(&maps.wd); prefetch_map(&maps.out);
      }
      __syncwarp();
      if (b < NFFN) {
        mbar_wait(bar_go2, 0);
        const __nv_bfloat16* pg = ((b & 1) ? P.w_up : P.w_gate) + (b >> 1) * 64 + (size_t)t2 * FF;
        const __nv_bfloat16* pd = P.w_down + (size_t)b * 32768 + t2 * 64;
        PROF(2, t2 == 0, 13);
#pragma unroll 1
        for (int i = 0; i < WN; i += WB) {
          uint32_t v[WB];
#pragma unroll
          for (int u = 0; u < WB; u++) {
            const int k = i + u;
            asm volatile("ld.global.cg.L2::128B.u32 %0, [%1];" : "=r"(v[u]) : "l"(k < 16 ? pg + (size_t)k * 64 * FF : pd + (k - 16) * 4096));
          }
#pragma unroll
          for (int u = 1; u < WB; u++) v[0] ^= v[u];
          sts1(par + PAR_SINK + t2 * 4, v[0]);
        }
        PROF(2, t2 == 0, 14);
      }
      const uint32_t tag = epoch % 3 + 1;
      mbar_wait(bar_go, 0);
      bar_sync(4, 64);
      if (warp == 10) {
        const uint32_t* src = g_mod + 2 * DM + cj * 128 + lane * 4;
        const uint2 wr = *reinterpret_cast<const uint2*>(P.w_r + cj * 128 + lane * 4);
        uint4 vga, vsb, vcb, vgb;
        uint32_t n = 0;
        do {
          vga = ld_relaxed4(src); vsb = ld_relaxed4(src + DM); vcb = ld_relaxed4(src + 2 * DM); vgb = ld_relaxed4(src + 3 * DM);
          watchdog(n);
        } while (!__all_sync(0xffffffffu, tag_ok(vga, tag) && tag_ok(vsb, tag) && tag_ok(vcb, tag) && tag_ok(vgb, tag)));
        const float c0 = rbf(1.f + bf_hi(vcb.x)), c1 = rbf(1.f + bf_hi(vcb.y)), c2 = rbf(1.f + bf_hi(vcb.z)), c3 = rbf(1.f + bf_hi(vcb.w));
        const float a0 = c0 * bf_lo(wr.x), a1 = c1 * bf_hi(wr.x), a2 = c2 * bf_lo(wr.y), a3 = c3 * bf_hi(wr.y);
        const uint32_t h0 = pack_bf(a0, a1), h1 = pack_bf(a2, a3);
        const uint32_t t1 = par + PAR_T1 + (lane >> 2) * 64 + (lane & 1) * 32 + (lane & 2) * 2;
        sts1(t1, h0); sts1(t1 + 8, pack_bf(a0 - bf_lo(h0), a1 - bf_hi(h0)));
        sts1(t1 + 16, h1); sts1(t1 + 24, pack_bf(a2 - bf_lo(h1), a3 - bf_hi(h1)));
        const uint32_t tg = par + PAR_SINK + (lane >> 3) * 64 + (lane & 1) * 32 + (lane & 6) * 2;
        sts1(tg, __byte_perm(vga.x, vga.y, 0x7632)); sts1(tg + 16, __byte_perm(vga.z, vga.w, 0x7632));
        sts4(par + PAR_T2 + lane * 32, make_uint4(pack_bf(c0, c1), __byte_perm(vsb.x, vsb.y, 0x7632), __byte_perm(vgb.x, vgb.y, 0x7632), __byte_perm(vga.x, vga.y, 0x7632)));
        sts4(par + PAR_T2 + lane * 32 + 16, make_uint4(pack_bf(c2, c3), __byte_perm(vsb.z, vsb.w, 0x7632), __byte_perm(vgb.z, vgb.w, 0x7632), __byte_perm(vga.z, vga.w, 0x7632)));
      } else {
        const uint4 g = poll4((lane & 2) ? g_mod + 8 - (lane & 1) * 4 : g_mod + 5 * DM + b * 8 + (lane & 1) * 4, tag);
        sts1(par + PAR_CONST + 60, 0);
        if (lane < 2) sts4(par + PAR_CONST + 16 + lane * 16, g);
        else if (lane < 4) sts2(par + PAR_CONST + (lane - 2) * 8, __float_as_uint(untag_sum(g.x, g.y) + untag_sum(g.z, g.w)), epoch);
      }
      __syncwarp();
#pragma unroll 4
      for (int q = 0; q < 32; q++) st_b128(g_xch + ((size_t)b * 8 * 256 + q * 64 + t2) * 4, (epoch & 1) << 16, 0, 0, 0);
      for (int q = 0; q < 2; q++) st_relaxed4(g_stats + ((size_t)cj * SEQ + rb * 128 + q * 64 + t2) * 4, 0, 0, 0, 0);
      if (b < NFFN)
        for (int q = 0; q < 4; q++) st_relaxed4(g_ypart + ((size_t)(q * 32 + (t2 >> 1)) * NFFN + b) * 8 + (t2 & 1) * 4, 0, 0, 0, 0);
      st_relaxed4(g_row + rb * 2 * DM + (t2 >> 5) * DM + cj * 128 + (t2 & 31) * 4, 0, 0, 0, 0);
      __threadfence();
      mbar_arrive(bar_par);
      mbar_wait(bar_gate, 0);
      uint32_t have = 0, n = 0;
      while (true) {
        const uint32_t st = lds1(par + PAR_CONST + 60) >> 7;
        if ((st & 31) != have) {
          const uint32_t* hsrc = g_row + (st & 15) * 2 * DM + t2 * 4;
          uint4 hv[4];
          bool ok = true;
#pragma unroll
          for (int i = 0; i < 4; i++) hv[i] = ld_pairs(hsrc + i * 256);
#pragma unroll
          for (int i = 0; i < 4; i++) {
            sts2(base + ((FT_G >> i * 4) & 15) * UNIT + (warp & 1) * 8192 + 256 + lane * 8, hv[i].x, hv[i].z);
            ok = ok && hv[i].y == tag && hv[i].w == tag;
          }
          have = __all_sync(0xffffffffu, ok) ? st & 31 : 0;
        }
        if ((st ^ have) == 32) break;
        watchdog(n);
      }
      mbar_arrive(bar_sel);
    }
    __syncwarp();
    cluster_arrive();
    {
      const uint32_t tag = epoch % 3 + 1, t3 = tid - 256;
      mbar_wait(bar_win, 0);
      uint2 win = lds2(par + PAR_CONST + 56);
      win.y &= 0x7ff;
      const uint32_t* fsrc = g_row + (win.y >> 7) * 2 * DM + (b >> 1) * 16 + (t3 & 3) * 4 + (b & 1) * 2;
      const uint32_t* ysrc = g_ypart + (size_t)b * NFFN * 8 + min(t3, NFFN - 1) * 4;
      uint2 fh = ld_pair(fsrc), fx = ld_pair(fsrc + DM);
      if (PSL) __nanosleep(PSL);
      uint4 ya = ld_relaxed4(ysrc), yb = ld_relaxed4(ysrc + NFFN * 4);
      const float rwin = __uint_as_float(((int)win.x < 0 ? win.x & 0x7fffffffu : ~win.x) & ~0x1ffu);
      const float rs = rbf(rcp(1.f + __expf(-rbf(rwin))));
      uint32_t n = 0;
      while (__any_sync(0xffffffffu, fh.y != tag || fx.y != tag)) { fh = ld_pair(fsrc); fx = ld_pair(fsrc + DM); watchdog(n); }
      while (!__all_sync(0xffffffffu, tag_ok(ya, tag) && tag_ok(yb, tag))) {
        if (!tag_ok(ya, tag)) ya = ld_relaxed4(ysrc);
        if (!tag_ok(yb, tag)) yb = ld_relaxed4(ysrc + NFFN * 4);
        watchdog(n);
      }
      __syncwarp();
      PROF(8, t3 == 0, 5);
      float y0 = untag_sum(ya.x, yb.x), y1 = untag_sum(ya.y, yb.y), y2 = untag_sum(ya.z, yb.z), y3 = untag_sum(ya.w, yb.w);
      const bool u1 = lane & 2, u2 = lane & 4;
      y0 = (u1 ? y2 : y0) + __shfl_xor_sync(0xffffffffu, u1 ? y0 : y2, 2);
      y1 = (u1 ? y3 : y1) + __shfl_xor_sync(0xffffffffu, u1 ? y1 : y3, 2);
      y0 = (u2 ? y1 : y0) + __shfl_xor_sync(0xffffffffu, u2 ? y0 : y1, 4);
      y0 += __shfl_xor_sync(0xffffffffu, y0, 8);
      if (!(lane & 8)) sts1(par + PAR_RED + 64 + (t3 >> 4) * 32 + ((lane & 1) * 4 + (lane & 2) + ((lane >> 2) & 1)) * 4, __float_as_uint(y0));
      bar_sync(4, 128);
      if (t3 < 4) {
        y0 = 0.f; y1 = 0.f;
#pragma unroll
        for (int w4 = 0; w4 < 7; w4++) {
          const uint2 v = lds2(par + PAR_RED + 64 + w4 * 32 + t3 * 8);
          y0 += __uint_as_float(v.x); y1 += __uint_as_float(v.y);
        }
        const uint2 gv = lds2(par + PAR_CONST + 16 + t3 * 8);
        const uint32_t upd = hmul2(pack_bf(y0, y1), pack_bf(rs, rs));
        *reinterpret_cast<uint32_t*>(P.out + (size_t)win.y * DM + b * 8 + t3 * 2) =
            hadd2(fx.x, hmul2(__byte_perm(gv.x, gv.y, 0x7632), hadd2(fh.x, upd)));
        if (b == 0 && t3 == 0) st_relaxed(&g_epoch, epoch + 1);
      }
      PROF(31, t3 == 0, 36);
    }
    cluster_wait();
  } else {
    const int wg = warp >> 2;

    uint32_t tag;
    {
      uint32_t* const pmod = g_modp + rank * 2 * DM + (b >> 1) * 32 + lane;
      uint32_t* const pln = g_ln1 + (rb * 128 + cj * 16 + warp) * 4;
      uint32_t sc[8];
#pragma unroll
      for (int k = 0; k < 8; k++) sc[k] = ldg_nc1(P.c + rank * 512 + warp * 64 + k * 8 + (lane & 3) * 2);
      const uint32_t epoch = ld_relaxed(&g_epoch);
      if (warp == 0) st_relaxed(pmod, 0);
      if (lane == 0) { st_b128(pln, 0, 0, 0, 0); st_b128(pln + 32, 0, 0, 0, 0); }
      asm volatile("setmaxnreg.inc.sync.aligned.u32 232;");
      bar_sync(1, 320);
#pragma unroll
      for (int k = 0; k < 8; k++) sc[k] = pack_bf(silu_f(bf_lo(sc[k])), silu_f(bf_hi(sc[k])));
      keep(sc);
      tag = epoch % 3 + 1;
#pragma unroll
      for (int part = 0; part < 4; part++) {
        if (!(part & 1)) {
          const uint32_t xa = base + (2 + part / 2) * GST_BYTES + warp * 2048 + lane * 16;
          mbar_wait(bar_hx + part * 4, 0);
          float s0 = 0.f, s1 = 0.f, q0 = 0.f, q1 = 0.f;
#pragma unroll
          for (int q = 0; q < 4; q++) {
            const uint4 xv = lds4(xa + q * 512);
            const uint32_t u[4] = {xv.x, xv.y, xv.z, xv.w};
#pragma unroll
            for (int e = 0; e < 4; e++) { const float lo = bf_lo(u[e]), hi = bf_hi(u[e]); s0 += lo; s1 += hi; q0 += lo * lo; q1 += hi * hi; }
          }
          s0 += s1; q0 += q1;
#pragma unroll
          for (int o = 16; o > 0; o >>= 1) { s0 += __shfl_xor_sync(0xffffffffu, s0, o); q0 += __shfl_xor_sync(0xffffffffu, q0, o); }
          const float mean = s0 * (1.f / DM);
          float mb, sd;
          ln_scalars(mean, fmaxf(q0 * (1.f / DM) - mean * mean, 0.f), mb, sd);
          uint32_t ih, il;
          split_inv(sd, ih, il);
          if (lane == 0) st_b128(pln + part * 16, pack_bf(mb, mb), ih, il, tag);
          PROF(1, tid == 0 && part == 2, 4);
        } else if (late == (part == 3)) {
          const uint32_t fr = (lane & 7) + (lane >> 4) * 8, tq = lane & 3;
          const uint32_t wa = stage + warp * 4096 + fr * 64 + ((((lane >> 3) & 1) ^ ((fr >> 1) & 3)) << 4);
          float d0[4] = {0.f, 0.f, 0.f, 0.f}, d1[4] = {0.f, 0.f, 0.f, 0.f};
          mbar_wait(bar_hw, 0);
#pragma unroll
          for (int ks = 0; ks < 4; ks++) {
            uint32_t w[8];
            ldmatrix4t(wa + ks * 1024, w[0], w[1], w[2], w[3]);
            ldmatrix4t((wa ^ 32) + ks * 1024, w[4], w[5], w[6], w[7]);
            mma16816(d0, w[0], w[1], w[2], w[3], sc[2 * ks], sc[2 * ks + 1]);
            mma16816(d1, w[4], w[5], w[6], w[7], sc[2 * ks], sc[2 * ks + 1]);
          }
          sts1(base + 2 * GST_BYTES + warp * 2048 + (tq * 8 + (lane >> 2)) * 4, __float_as_uint((tq & 2) ? ((tq & 1) ? d1[2] : d1[0]) : ((tq & 1) ? d0[2] : d0[0])));
          bar_sync(1, 256);
          if (warp == 0) {
            float s = 0.f;
#pragma unroll
            for (int w8 = 0; w8 < 8; w8++) s += __uint_as_float(lds1(base + 2 * GST_BYTES + w8 * 2048 + lane * 4));
            st_relaxed(pmod, (__float_as_uint(s) & ~3u) | tag);
          }
          PROF(1, tid == 0, 3);
        }
      }
      cluster_wait();
      if (wg == 1) bar_arrive(2, 256);
    }

    float f0 = 0.f, f1 = 0.f;
    const uint32_t rempty = lane < 2 ? mapa(bempty, lane & 1) : 0;
    constexpr uint32_t GE = NSLOT * 8 + 32;
    float o[64], s[64];
#pragma unroll 1
    for (int ps = 0; ps < 3; ps++) {
      {
        const uint32_t xt = ps == 1 ? XT1 : XT2, wt = ps == 1 ? WT1 : WT2;
        const int nst = ps == 2 ? 28 : 14;
        if (ps == 0) {
          float ga[64], gb[64];
#pragma unroll
          for (int i = 0; i < 64; i++) { ga[i] = 0.f; gb[i] = 0.f; }
          uint32_t a[2][16];
          const uint32_t l = fresh_lane();
          uint32_t fa[4];
#pragma unroll
          for (int kk = 0; kk < 4; kk++) fa[kk] = (base + wg * 8192 + frag_offset(warp)) ^ (kk * 32);
          const uint32_t mt = par + (l & 3) * 16;
          auto fetch = [&](int i, uint32_t (&f)[16], uint32_t z) {
            mbar_wait(xfull + (i & 3) * 8, i >> 2);
#pragma unroll
            for (int kk = 0; kk < 4; kk++) ldmatrix4(fa[kk] + (i & 3) * GST_BYTES + z, f[4 * kk], f[4 * kk + 1], f[4 * kk + 2], f[4 * kk + 3]);
          };
          const bool oddw = warp & 2;
          uint4 r0, r1;
          {
            const uint32_t t7 = (warp & 1) * 64 + (l >> 4) * 32 + (l & 15);
            const uint32_t* pm = g_modp + wg * DM + ((cj * 128 + t7 * 4) & (DM - 1));
            const uint32_t* pr = g_ln1 + (rb * 128 + warp * 16 + (l >> 2)) * 4;
            uint4 m0 = make_uint4(tag, tag, tag, tag), m1 = m0;
            if (!oddw) { m0 = ld_relaxed4(pm); m1 = ld_relaxed4(pm + 2 * DM); }
            r0 = ld_b128(pr); r1 = ld_b128(pr + 32);
            fetch(0, a[0], 0); fetch(1, a[1], 0);
            uint32_t n = 0;
            bool written = false;
#pragma unroll 1
            while (true) {
              uint32_t miss;
              asm volatile("{ .reg .pred p0, p1, p2, p3; .reg .b32 t, u;\n"
                           "lop3.b32 t, %1, %2, %19, 0x7e; lop3.b32 u, %3, %4, %19, 0x7e; or.b32 t, t, u; and.b32 t, t, 3; setp.ne.u32 p0, t, 0;\n"
                           "lop3.b32 t, %5, %6, %19, 0x7e; lop3.b32 u, %7, %8, %19, 0x7e; or.b32 t, t, u; and.b32 t, t, 3; setp.ne.u32 p1, t, 0;\n"
                           "setp.ne.u32 p2, %12, %19; setp.ne.u32 p3, %16, %19;\n"
                           "@p0 ld.relaxed.gpu.global.v4.u32 {%1, %2, %3, %4}, [%17];\n"
                           "@p1 ld.relaxed.gpu.global.v4.u32 {%5, %6, %7, %8}, [%17 + 8192];\n"
                           "@p2 ld.relaxed.gpu.global.v4.u32 {%9, %10, %11, %12}, [%18];\n"
                           "@p3 ld.relaxed.gpu.global.v4.u32 {%13, %14, %15, %16}, [%18 + 128];\n"
                           "or.pred p0, p0, p1; or.pred p2, p2, p3; vote.sync.any.pred p0, p0, 0xffffffff; vote.sync.any.pred p2, p2, 0xffffffff;\n"
                           "selp.u32 t, 1, 0, p0; selp.u32 u, 2, 0, p2; or.b32 %0, t, u; }"
                           : "=r"(miss), "+r"(m0.x), "+r"(m0.y), "+r"(m0.z), "+r"(m0.w), "+r"(m1.x), "+r"(m1.y), "+r"(m1.z), "+r"(m1.w),
                             "+r"(r0.x), "+r"(r0.y), "+r"(r0.z), "+r"(r0.w), "+r"(r1.x), "+r"(r1.y), "+r"(r1.z), "+r"(r1.w)
                           : "l"(pm), "l"(pr), "r"(tag) : "memory");
              if (!(miss & 1) && !written) {
                written = true;
                if (!oddw) write_table(par, wg, t7, m0, m1);
                mbar_arrive(bar_mod);
              }
              if (!miss) break;
              watchdog(n);
            }
          }
          const uint32_t zero = r0.w ^ tag;
          auto normalize = [&](uint32_t (&f)[16]) {
#pragma unroll
            for (int k = 0; k < 16; k += 2) { f[k] = ln_norm(f[k], r0.x, r0.y, r0.z); f[k + 1] = ln_norm(f[k + 1], r1.x, r1.y, r1.z); }
          };
          auto modulate = [&](int i, uint32_t (&f)[16]) {
#pragma unroll
            for (int kk = 0; kk < 4; kk++) {
              const uint4 m = lds4(mt + slice_of(i) * 256 + kk * 64);
              f[4 * kk] = MODUL(f[4 * kk], m.x, m.z); f[4 * kk + 1] = MODUL(f[4 * kk + 1], m.x, m.z);
              f[4 * kk + 2] = MODUL(f[4 * kk + 2], m.y, m.w); f[4 * kk + 3] = MODUL(f[4 * kk + 3], m.y, m.w);
            }
            keep(f);
            mbar_arrive_pred(xempty + (i & 3) * 8, l == 0);
          };
          auto publish = [&](int u, uint32_t (&f)[16]) {
#pragma unroll
            for (int kk = 0; kk < 4; kk++) stmatrix4(fa[kk] + OFF_STAGE + u * UNIT, f[4 * kk], f[4 * kk + 1], f[4 * kk + 2], f[4 * kk + 3]);
            __syncwarp();
            mbar_arrive_pred(bar_hpub + u * 8, l == 0);
          };
          auto multiply = [&](int i, uint32_t (&f)[16]) {
            mbar_wait(gfull + (i & 3) * 8, i >> 2);
            const uint64_t db = make_desc(base + (i & 3) * GST_BYTES + UNIT, 8192, 1024);
            wg_fence();
#pragma unroll
            for (int kk = 0; kk < 4; kk++) mma256_rs(ga, gb, f[4 * kk], f[4 * kk + 1], f[4 * kk + 2], f[4 * kk + 3], db + kk * 128);
            wg_commit();
          };
          auto next = [&](int i, uint32_t (&f)[16]) {
            wg_wait<1>();
            mbar_arrive_cl(rempty, GE + ((i + 2) & 3) * 8);
            uint32_t z = zero;
#pragma unroll
            for (int k = 0; k < 16; k += 2) asm volatile("lop3.b32 %0, %1, %2, %0, 0xA8;" : "+r"(z) : "r"(f[k]), "r"(f[k + 1]));
            fetch(i, f, z);
            normalize(f);
            if (i == 2) { keep(f); mbar_wait(bar_mod2, 0); }
            modulate(i, f); multiply(i, f);
          };
          normalize(a[0]); normalize(a[1]);
          keep(a[0]); keep(a[1]);
          mbar_wait(bar_mod, 0);
          PROF(1, tid == 0, 2);
          modulate(0, a[0]); multiply(0, a[0]); publish(0, a[0]);
          modulate(1, a[1]); multiply(1, a[1]);
#pragma unroll 1
          for (int i = 2; i < NRS; i += 2) {
            next(i, a[0]);
            if (i == 2) publish(1, a[0]);
            next(i + 1, a[1]);
          }
          wg_wait<1>();
          mbar_arrive_cl(rempty, GE + ((NRS + 2) & 3) * 8);
#pragma unroll 1
          for (int i = NRS; i < 14; i++) {
            mbar_wait(xfull + (i & 3) * 8, (i >> 2) & 1);
            mbar_wait(gfull + (i & 3) * 8, (i >> 2) & 1);
            const uint32_t xa = base + (i & 3) * GST_BYTES;
            const uint64_t da = make_desc(xa + wg * 8192, 16, 1024), db = make_desc(xa + UNIT, 8192, 1024);
            if (i == 13) bar_sync(2 + wg, 256);
            wg_fence();
#pragma unroll
            for (int kk = 0; kk < 4; kk++) mma256_ss(ga, gb, da + kk * 2, db + kk * 128, 1);
            wg_commit();
            if (i == 13) bar_arrive(3 - wg, 256);
            wg_wait<1>();
            uint32_t z = zero;
#pragma unroll
            for (int k = 0; k < 16; k += 2) asm volatile("lop3.b32 %0, %1, %2, %0, 0xA8;" : "+r"(z) : "r"(a[1][k]), "r"(a[1][k + 1]));
            mbar_arrive_cl(rempty, GE + ((i + 3) & 3) * 8 + z);
            mbar_arrive_pred(xempty + ((i + 3) & 3) * 8, l == 0 && i != NRS);
          }
          mbar_wait(xfull + 16, 1);
          wg_wait<0>();
          keep(ga); keep(gb);
#pragma unroll
          for (int i = 0; i < 64; i++) {
            asm volatile("mov.b32 %0, %1;" : "=f"(s[i]) : "f"(ga[i]));
            asm volatile("mov.b32 %0, %1;" : "=f"(o[i]) : "f"(gb[i]));
          }
        } else {
          float ga[64], gb[64];
#pragma unroll
          for (int i = 0; i < 64; i++) {
            asm volatile("mov.b32 %0, %1;" : "=f"(ga[i]) : "f"(s[i]));
            asm volatile("mov.b32 %0, %1;" : "=f"(gb[i]) : "f"(o[i]));
          }
#pragma unroll 1
          for (int i = 0; i < nst; i++) {
            mbar_wait(gfull + (i & 3) * 8, (i >> 2) & 1);
            const uint64_t da = make_desc(base + unit_of(xt, i & 3) + wg * 8192, 16, 1024), db = make_desc(base + unit_of(wt, i & 3), 8192, 1024);
            if (i == nst - 1) bar_sync(2 + wg, 256);
            wg_fence();
#pragma unroll
            for (int kk = 0; kk < 4; kk++) mma256_ss(ga, gb, da + kk * 2, db + kk * 128, kk ? 1 : i);
            wg_commit();
            if (i == nst - 1) bar_arrive(3 - wg, 256);
            wg_wait<1>();
            mbar_arrive_cl(rempty, GE + ((i + 3) & 3) * 8, i != 0);
            PROF(4, tid == 0 && (i & 3) == 0, 40 + (ps - 1) * 4 + i / 4);
          }
          wg_wait<0>();
          keep(ga); keep(gb);
#pragma unroll
          for (int i = 0; i < 64; i++) {
            asm volatile("mov.b32 %0, %1;" : "=f"(s[i]) : "f"(ga[i]));
            asm volatile("mov.b32 %0, %1;" : "=f"(o[i]) : "f"(gb[i]));
          }
        }
        mbar_arrive_cl(rempty, GE + (ps == 2 ? 24 : 8));
        if (ps == 2) break;
      }
      const uint32_t qw = base + wg * 8192, qt = QT >> (16 * ps), at = ps ? AT1 : AT0;
      {
        const uint32_t wt = ps ? WT1 : WT0;
        const uint64_t da0 = make_desc(qw + unit_of(qt, 2), 16, 1024), da1 = make_desc(qw + unit_of(qt, 3), 16, 1024);
        const uint64_t db0 = make_desc(base + unit_of(wt, 2), 8192, 1024), db1 = make_desc(base + unit_of(wt, 3), 8192, 1024);
        mbar_wait(gfull + 16, 1);
        bar_sync(2 + wg, 256);
        wg_fence();
#pragma unroll
        for (int kk = 0; kk < 4; kk++) mma_ss<1>(s, da0 + kk * 2, db0 + kk * 128, 1);
        wg_commit();
        mbar_wait(xfull + 24, 1);
        mbar_wait(gfull + 24, 1);
        wg_fence();
#pragma unroll
        for (int kk = 0; kk < 4; kk++) mma_ss<1>(s, da1 + kk * 2, db1 + kk * 128, 1);
        wg_commit();
        bar_arrive(3 - wg, 256);
        mbar_wait(ps == 0 ? bar_pread : bar_ofree + 8, 0);
        wg_wait<0>();
        keep(s);
        PROF(2, tid == 0, 8 + ps * 8);
        uint32_t q[32];
        pack_p(s, q);
#pragma unroll
        for (int i = 0; i < 4; i++) stmatrix4((qw + unit_of(qt, 0) + frag_offset(warp)) ^ (i << 5), q[4 * i], q[4 * i + 1], q[4 * i + 2], q[4 * i + 3]);
        keep(q);
        bar_sync(2 + wg, 256);
        wg_fence();
#pragma unroll
        for (int kk = 0; kk < 8; kk++) mma_ss<1>(o, (kk < 4 ? da0 : da1) + (kk & 3) * 2, (kk < 4 ? db0 : db1) + UNIT / 16 + (kk & 3) * 128, 1);
        wg_commit();
        mbar_wait(bfull, 0);
        wg_fence();
        const uint64_t dk = make_desc(base + unit_of(at, 0), 16, 1024);
#pragma unroll
        for (int kk = 0; kk < 8; kk++) mma_rs<0>(s, q[4 * kk], q[4 * kk + 1], q[4 * kk + 2], q[4 * kk + 3], dk + (kk >> 2) * 1024 + (kk & 3) * 2, kk != 0);
        wg_commit();
        bar_arrive(3 - wg, 256);
#pragma unroll
        for (int i = 4; i < 8; i++) stmatrix4((qw + unit_of(qt, 1) + frag_offset(warp)) ^ ((i & 3) << 5), q[4 * i], q[4 * i + 1], q[4 * i + 2], q[4 * i + 3]);
        wg_wait<1>();
        keep(o);
        mbar_arrive_cl(rempty, GE + 16);
        mbar_arrive_cl(rempty, GE + 24);
        store_chunk<0>(o, qw + unit_of(qt, 2) + frag_offset(warp));
        store_chunk<1>(o, qw + unit_of(qt, 3) + frag_offset(warp));
        wg_wait<0>();
        keep(s);
        mbar_arrive_cl(rempty, 0);
      }
      PROF(4, tid == 0 && ps == 1, 61);
      float l0 = 0.f, l1 = 0.f;
      auto step = [&](auto odd_c, const int j, uint32_t (&pw)[32], uint32_t (&pr)[32]) {
        constexpr bool ODD = decltype(odd_c)::value;
        const bool first = !ODD && (j & 2) == 0, last = ODD && j == 7;
        const uint32_t ph = (j >> 1) & 1;
        float i0, i1, a0, a1;
        const bool so = !ODD && j == 4;
        if (so) { i0 = inv_quad_sum(l0); i1 = inv_quad_sum(l1); l0 = 0.f; l1 = 0.f; }
        bool redo = !ODD && (j | ps) == 0;
        while (true) {
          if (redo) {
            float m0 = fmaxf(s[0], s[1]), m1 = fmaxf(s[2], s[3]);
#pragma unroll
            for (int i = 1; i < 16; i++) { m0 = fmaxf(m0, fmaxf(s[4 * i], s[4 * i + 1])); m1 = fmaxf(m1, fmaxf(s[4 * i + 2], s[4 * i + 3])); }
            m0 = fmaxf(m0, __shfl_xor_sync(0xffffffffu, m0, 1)); m1 = fmaxf(m1, __shfl_xor_sync(0xffffffffu, m1, 1));
            m0 = fmaxf(m0, __shfl_xor_sync(0xffffffffu, m0, 2)); m1 = fmaxf(m1, __shfl_xor_sync(0xffffffffu, m1, 2));
            m0 *= SCL2; m1 *= SCL2;
            if (!first) {
              m0 = fmaxf(m0, f0); m1 = fmaxf(m1, f1);
              const float c0 = ex2(f0 - m0), c1 = ex2(f1 - m1);
              l0 *= c0; l1 *= c1;
              wg_wait<0>();
              keep(o);
#pragma unroll
              for (int i = 0; i < 16; i++) { o[4 * i] *= c0; o[4 * i + 1] *= c0; o[4 * i + 2] *= c1; o[4 * i + 3] *= c1; }
            }
            f0 = m0; f1 = m1;
          }
          float b0 = 0.f, b1 = 0.f;
          a0 = 0.f; a1 = 0.f;
#pragma unroll
          for (int i = 0; i < 16; i++) {
            const float e0 = ex2(fmaf(s[4 * i], SCL2, -f0)), e1 = ex2(fmaf(s[4 * i + 1], SCL2, -f0));
            const float e2 = ex2(fmaf(s[4 * i + 2], SCL2, -f1)), e3 = ex2(fmaf(s[4 * i + 3], SCL2, -f1));
            a0 += e0; b0 += e1; a1 += e2; b1 += e3;
            pw[2 * i] = pack_bf(e0, e1); pw[2 * i + 1] = pack_bf(e2, e3);
            if (i == VREL) {
#pragma unroll
              for (int k = 0; k < 2 * VREL + 2; k++) asm volatile("" : "+r"(pw[k])::"memory");
              mbar_wait(bar_mod, 0);
              wg_wait<0>();
              mbar_arrive_cl(rempty, ODD ? 16 : 0, !redo && (ODD || j));
#pragma unroll
              for (int k = 4 * VREL + 4; k < 64; k++) asm volatile("" : "+f"(s[k])::"memory");
            }
          }
          a0 += b0; a1 += b1;
          if (redo) break;
          redo = __any_sync(0xffffffffu, !(a0 + a1 < 0x1p90f));
          if (first) {
            uint32_t m0 = __ballot_sync(0xffffffffu, a0 > 0x1p-80f), m1 = __ballot_sync(0xffffffffu, a1 > 0x1p-80f);
            m0 |= m0 >> 1; m1 |= m1 >> 1; m0 |= m0 >> 2; m1 |= m1 >> 2;
            redo = redo || (m0 & m1 & 0x11111111u) != 0x11111111u;
          }
          if (!redo) break;
        }
        l0 += a0; l1 += a1;
        keep(pw);
        keep(o);
        if (so) store_chunk<0>(o, i0, i1, qw + unit_of(qt, 0) + frag_offset(warp));
        keep(o);
        if (j == (ODD ? 5 : 0)) { fence_async_smem(); if (ODD) mbar_arrive(bar_ofull + wg * 8); }
        mbar_wait(bfull + (ODD ? 24 : 8), ph);
        bar_sync(2 + wg, 256);
        if (!last) {
          const uint32_t qn = qt >> (j >= 3 ? 8 : 0);
          wg_fence();
          issue_qk(s, qw + unit_of(qn, 0), qw + unit_of(qn, 1), base + unit_of(at, ODD ? 3 : 1));
          wg_commit();
          mbar_wait(bfull + (ODD ? 0 : 16), ODD ? ph ^ 1 : ph);
        }
        if (so) { store_chunk<1>(o, i0, i1, qw + unit_of(qt, 1) + frag_offset(warp)); keep(o); }
        wg_fence();
        issue_pv(o, pw, base + unit_of(at, ODD ? (last ? 3 : 0) : 2), !first);
        wg_commit();
        bar_arrive(3 - wg, 256);
        wg_wait<1>();
        keep(s);
        mbar_arrive_cl(rempty, ODD ? 24 : 8, !last);
        PROF(4, tid == 0 && ps == 1, 51 + j);
      };
      uint32_t pa[32], pb[32];
#pragma unroll 1
      for (int j = 0; j < 8; j += 2) {
        step(std::false_type{}, j, pa, pb);
        step(std::true_type{}, j + 1, pb, pa);
      }
      {
        const float i0 = inv_quad_sum(l0), i1 = inv_quad_sum(l1);
        wg_wait<0>();
        keep(o);
        mbar_arrive_cl(rempty, 24);
        store_chunk<0>(o, i0, i1, qw + unit_of(qt, 2) + frag_offset(warp));
        store_chunk<1>(o, i0, i1, qw + unit_of(qt, 3) + frag_offset(warp));
        fence_async_smem();
        mbar_arrive(bar_ofull + 16 + wg * 8);
      }
      PROF(2, tid == 0, 10 + ps * 8);
    }

    const int ln = fresh_lane(), g = ln >> 2, tq = ln & 3, ct = warp * 32 + ln;
    const bool lane0 = ln == 0;
    const int lrow0 = warp * 16 + g;
    const int grow0 = rb * 128 + lrow0;
    const uint32_t res = base + OFF_RES, trow = res + wg * 8192 + frag_offset(warp);
    uint32_t xr[32];
    uint4 sv[4], own;
    uint32_t* sp[4];
#pragma unroll
    for (int k = 0; k < 4; k++) sp[k] = g_stats + ((((tq >> 1) * 4 + k) ^ cj) * SEQ + grow0 + (tq & 1) * 8) * 4;
    {
      const uint64_t da = make_desc(base + wg * 8192, 16, 1024), db = make_desc(base, 8192, 1024);
      constexpr int U = UNIT / 16;
#define HALF_STAGE(acc, xu, wu) _Pragma("unroll") for (int kk = 0; kk < 4; kk++) mma_ss<1>(acc, da + (xu) * U + kk * 2, db + (wu) * U + kk * 128, 1)
      PROF(10, ct == PT, 19); STAMP(0);
      cluster_arrive();
      mbar_wait(gfull, 1);
      mbar_wait(gfull + 8, 1);
      bar_sync(2 + wg, 256);
      wg_fence();
      HALF_STAGE(o, 7, 1);
      HALF_STAGE(o, 8, 3);
      wg_commit();
      STAMP(16);
      mbar_wait(gfull + 16, 1);
      STAMP(17);
      wg_fence();
      HALF_STAGE(o, 6, 11);
      wg_commit();
      bar_arrive(3 - wg, 256);
      mbar_wait(bar_par, 0);
      uint32_t* xo = g_xch + ((size_t)b * 8 * 256 + ct) * 4;
      const uint32_t* xi = g_xch + ((size_t)(b ^ 2) * 8 * 256 + ct) * 4;
      const uint32_t par1 = (~lds1(par + PAR_CONST + 4) & 1) << 16;
      wg_wait<1>();
      mbar_arrive_pred(bar_rel, lane0);
      wg_wait<0>();
      keep(o);
      mbar_arrive_pred(bar_ring, lane0);
      PROF(8, ct == PT, 20); STAMP(1);
#define SEND(i) st_b128(xo + (i) * 1024, (pack_bf(o[8 * (i)], o[8 * (i) + 1]) & ~0x10000u) | par1, pack_bf(o[8 * (i) + 2], o[8 * (i) + 3]), \
                        pack_bf(o[8 * (i) + 4], o[8 * (i) + 5]), pack_bf(o[8 * (i) + 6], o[8 * (i) + 7]))
#pragma unroll
      for (int i = 0; i < NS1; i++) SEND(i);
      PROF(8, ct == PT, 21); STAMP(2);
      bar_sync(2 + wg, 256);
      wg_fence();
      HALF_STAGE(s, 7, 0);
      HALF_STAGE(s, 8, 2);
      HALF_STAGE(s, 6, 10);
      wg_commit();
      bar_arrive(3 - wg, 256);
      STAMP(18);
      mbar_wait(gfull + 24, 1);
#pragma unroll
      for (int i = NS1; i < 8; i++) SEND(i);
      uint4 v[8];
#pragma unroll
      for (int i = 0; i < LD1; i++) v[i] = ld_b128(xi + i * 1024);
      STAMP(19);
      mbar_wait(bar_xres, 0);
      wg_wait<0>();
      mbar_arrive_pred(bar_ring + 8, lane0);
      bar_sync(2 + wg, 256);
      STAMP(20);
#pragma unroll
      for (int i = LD1; i < LD2; i++) v[i] = ld_b128(xi + i * 1024);
      mbar_wait(bar_xres, 0);
      wg_fence();
      HALF_STAGE(s, 9, 4);
      wg_commit();
      mbar_wait(bar_rx, 0);
      wg_fence();
      HALF_STAGE(s, 1, 5);
      wg_commit();
      bar_arrive(3 - wg, 256);
      STAMP(21);
#pragma unroll
      for (int i = LD2; i < 8; i++) v[i] = ld_b128(xi + i * 1024);
      if (LD2 < 8) mbar_wait(bar_xres, 0);
      wg_wait<0>();
      keep(s);
      mbar_arrive_pred(bar_ring + 16, lane0);
      PROF(10, ct == PT, 23); STAMP(4);
#pragma unroll
      for (int i = 0; i < 16; i += 2) ldmatrix4((trow ^ ((i & 7) << 4)) + (i >> 3) * 16384, xr[2 * i], xr[2 * i + 1], xr[2 * i + 2], xr[2 * i + 3]);
      uint32_t ga[16];
      uint4 bw[8];
#pragma unroll
      for (int i = 0; i < 8; i++) {
        if (!(i & 1)) {
          const uint4 t = lds4(par + PAR_SINK + i * 32 + tq * 16);
          ga[2 * i] = t.x; ga[2 * i + 1] = t.y; ga[2 * i + 2] = t.z; ga[2 * i + 3] = t.w;
        }
        bw[i] = lds4(par + PAR_T1 + i * 64 + tq * 16);
        if (!(g & 1)) { bw[i].x = 0x3f803f80u; bw[i].y = 0x3f803f80u; }
      }
      uint32_t pk[32];
      pack_p(s, pk);
      keep(pk);
      {
        uint32_t n = 0, miss;
        do {
          miss = 0;
#pragma unroll
          for (int i = 0; i < 8; i++) miss |= v[i].x ^ par1;
          miss = __any_sync(0xffffffffu, miss & 0x10000u);
          if (miss) {
#pragma unroll
            for (int i = 0; i < 8; i++)
              asm volatile("{ .reg .pred p; .reg .b32 t; xor.b32 t, %0, %5; and.b32 t, t, 0x10000; setp.ne.u32 p, t, 0;\n"
                           "@p ld.relaxed.gpu.global.v4.u32 {%0, %1, %2, %3}, [%4]; }"
                           : "+r"(v[i].x), "+r"(v[i].y), "+r"(v[i].z), "+r"(v[i].w) : "l"(xi + i * 1024), "r"(par1) : "memory");
          }
          watchdog(n);
        } while (miss);
      }
      PROF(8, ct == PT, 22); STAMP(3);
      float ds[4] = {0.f, 0.f, 0.f, 0.f}, dl[4] = {0.f, 0.f, 0.f, 0.f}, q0[4] = {0.f, 0.f, 0.f, 0.f}, q1[4] = {0.f, 0.f, 0.f, 0.f};
#pragma unroll
      for (int i = 0; i < 8; i++) {
        const uint32_t u0 = hfma2(ga[2 * i], hadd2(pk[4 * i], v[i].x & ~0x10000u), xr[4 * i]);
        const uint32_t u1 = hfma2(ga[2 * i], hadd2(pk[4 * i + 1], v[i].y), xr[4 * i + 1]);
        const uint32_t u2 = hfma2(ga[2 * i + 1], hadd2(pk[4 * i + 2], v[i].z), xr[4 * i + 2]);
        const uint32_t u3 = hfma2(ga[2 * i + 1], hadd2(pk[4 * i + 3], v[i].w), xr[4 * i + 3]);
        xr[4 * i] = u0; xr[4 * i + 1] = u1; xr[4 * i + 2] = u2; xr[4 * i + 3] = u3;
        mma16816(ds, u0, u1, u2, u3, bw[i].x, bw[i].y);
        mma16816(dl, u0, u1, u2, u3, bw[i].z, bw[i].w);
        mma16816(q0, u0, u1, u2, u3, u0, u2);
        mma16816(q1, u0, u1, u2, u3, u1, u3);
      }
      const float sqa = __shfl_sync(0xffffffffu, (g & 1) ? q0[1] : q0[0], g * 4 + (g >> 1));
      const float sqb = __shfl_sync(0xffffffffu, (g & 1) ? q1[3] : q1[2], g * 4 + (g >> 1));
      own = (tq & 1) ? make_uint4(__float_as_uint(ds[2]), __float_as_uint(sqb), __float_as_uint(ds[3] + dl[3]), tag)
                                 : make_uint4(__float_as_uint(ds[0]), __float_as_uint(sqa), __float_as_uint(ds[1] + dl[1]), tag);
      if (tq < 2) st_b128(sp[0], own.x, own.y, own.z, own.w);
#pragma unroll
      for (int k = 0; k < 4; k++) sv[k] = make_uint4(0, 0, 0, 0);
    }
    PROF(8, ct == PT, 29); STAMP(5);
    uint32_t mm, ih, il;
    float rbest;
    uint32_t wf[128];
    const uint32_t frow = (ln & 7) + (ln >> 4) * 8;
    const uint32_t wfo = base + (warp & 1) * 8192 + frow * 64 + ((((ln >> 3) & 1) ^ ((frow >> 1) & 3)) << 4);
#define LOAD_WF(m) _Pragma("unroll") for (int f = 0; f < 16; f++) {                                                   \
      const int r = ((f >> 1) * 4 + (m) * 2 + (f & 1)) * 4;                                                           \
      ldmatrix4t(((wfo + unit_of((m) ? FT_U : FT_G, warp >> 1)) ^ ((f & 1) * 32)) + (f >> 1) * 1024, wf[r], wf[r + 1], wf[r + 2], wf[r + 3]); \
    }
    bool early;
    {
#pragma unroll
      for (int i = 0; i < 16; i += 2) stmatrix4((trow ^ ((i & 7) << 4)) + (i >> 3) * 16384, xr[2 * i], xr[2 * i + 1], xr[2 * i + 2], xr[2 * i + 3]);
      const uint4 cst = lds4(par + PAR_CONST);
      const float A1 = __uint_as_float(cst.x), A2 = __uint_as_float(cst.z);
      uint32_t n = 0;
      early = false;
#pragma unroll 1
      while (true) {
        uint32_t miss;
        asm volatile("{ .reg .pred p0, p1, p2, p3; .reg .b64 u, v; .reg .b128 w;\n"
                     "setp.ge.u32 p0, %22, 2; setp.ne.and.u32 p0, %4, %21, p0; setp.ne.u32 p1, %8, %21; setp.ne.u32 p2, %12, %21; setp.ne.u32 p3, %16, %21;\n"
                     "@p0 ld.relaxed.gpu.global.v4.u32 {%1, %2, %3, %4}, [%17];\n"
                     "@p1 ld.relaxed.gpu.global.v4.u32 {%5, %6, %7, %8}, [%18];\n"
                     "@p2 ld.relaxed.gpu.global.v4.u32 {%9, %10, %11, %12}, [%19];\n"
                     "@p3 ld.relaxed.gpu.global.v4.u32 {%13, %14, %15, %16}, [%20];\n"
                     "or.pred p0, p0, p1; or.pred p2, p2, p3; or.pred p0, p0, p2; vote.sync.any.pred p0, p0, 0xffffffff; selp.u32 %0, 1, 0, p0; }"
                     : "=r"(miss), "+r"(sv[0].x), "+r"(sv[0].y), "+r"(sv[0].z), "+r"(sv[0].w), "+r"(sv[1].x), "+r"(sv[1].y), "+r"(sv[1].z), "+r"(sv[1].w),
                       "+r"(sv[2].x), "+r"(sv[2].y), "+r"(sv[2].z), "+r"(sv[2].w), "+r"(sv[3].x), "+r"(sv[3].y), "+r"(sv[3].z), "+r"(sv[3].w)
                     : "l"(sp[0]), "l"(sp[1]), "l"(sp[2]), "l"(sp[3]), "r"(tag), "r"(tq) : "memory");
        if (!miss) break;
        if (!early && (b >= NFFN || __all_sync(0xffffffffu, mbar_test(bar_box + (warp >> 1) * 8, 0)))) {
          early = true;
          LOAD_WF(0);
          __syncwarp();
          mbar_arrive_pred(bar_gate, lane0);
        }
        watchdog(n);
      }
      const uint4 v0 = tq < 2 ? own : sv[0], v1 = sv[1], v2 = sv[2], v3 = sv[3];
      PROF(8, ct == PT, 30); STAMP(6);
      float su = (__uint_as_float(v0.x) + __uint_as_float(v1.x)) + (__uint_as_float(v2.x) + __uint_as_float(v3.x));
      float sq = (__uint_as_float(v0.y) + __uint_as_float(v1.y)) + (__uint_as_float(v2.y) + __uint_as_float(v3.y));
      float dt = (__uint_as_float(v0.z) + __uint_as_float(v1.z)) + (__uint_as_float(v2.z) + __uint_as_float(v3.z));
      su += __shfl_xor_sync(0xffffffffu, su, 2); sq += __shfl_xor_sync(0xffffffffu, sq, 2); dt += __shfl_xor_sync(0xffffffffu, dt, 2);
      const float m = su * (1.f / DM);
      float mb, sd;
      ln_scalars(m, fmaxf(sq * (1.f / DM) - m * m, 0.f), mb, sd);
      const float inv = rcp(sd);
      rbest = (dt - mb * A1) * inv + A2;
      mm = pack_bf(mb, mb);
      ih = pack_bf(inv, inv);
      const float lo = inv - bf_lo(ih);
      il = pack_bf(lo, lo);
    }
    int ibest;
    {
      const uint32_t bits = __float_as_uint(rbest);
      const uint32_t key = (((int)bits < 0 ? ~bits : bits | 0x80000000u) & ~0x1ffu) | ((127 - lrow0 - (tq & 1) * 8) << 2) | tag;
      sts1(par + PAR_RED + warp * 4, __reduce_max_sync(0xffffffffu, key));
      PROF(8, ct == PT, 38); STAMP(7);
      bar_sync(1, 256);
      const uint4 ka = lds4(par + PAR_RED), kb = lds4(par + PAR_RED + 16);
      const uint32_t k2 = max(max(max(ka.x, ka.y), max(ka.z, ka.w)), max(max(kb.x, kb.y), max(kb.z, kb.w)));
      if (ct == 0 && cj == 0) st_relaxed(g_cand + rb, k2);
      ibest = 127 - ((k2 >> 2) & 127);
    }
    PROF(8, ct == PT, 39); STAMP(8);
    if ((ibest >> 4) == warp) {
      const int src = (ibest & 7) * 4 + ((ibest >> 3) & 1), ch = g * 2;
      const uint32_t cm = __shfl_sync(0xffffffffu, mm, src), ch_ = __shfl_sync(0xffffffffu, ih, src), cl = __shfl_sync(0xffffffffu, il, src);
      const uint32_t xa = res + (ch >> 3) * 16384 + ibest * 128 + (((ch & 7) ^ (ibest & 7)) << 4) + tq * 4;
      const uint32_t x0 = lds1(xa), x1 = lds1(xa ^ 16);
      const uint2 p0 = lds2(par + PAR_T2 + ch * 64 + tq * 16), p1 = lds2(par + PAR_T2 + ch * 64 + 64 + tq * 16);
      uint32_t* dst = g_row + rb * 2 * DM + cj * 128 + ln * 4;
      st_pairs(dst, ln_mod(x0, cm, ch_, cl, p0.x, p0.y), ln_mod(x1, cm, ch_, cl, p1.x, p1.y), tag);
      st_pairs(dst + DM, x0, x1, tag);
      __syncwarp();
    }
    PROF(8, ct == PT, 37); STAMP(9);
    uint32_t wd[64];
    const uint32_t wda = base + unit_of(FT_D, warp >> 1) + (warp & 1) * 8192 + frow * 128 + ((((ln >> 3) & 1) ^ (ln & 7)) << 4);
#define LOAD_WD(f) ldmatrix4t((wda ^ ((((f) >> 1) & 3) * 32)) + ((f) >> 3) * 4096 + ((f) & 1) * 2048, wd[4 * (f)], wd[4 * (f) + 1], wd[4 * (f) + 2], wd[4 * (f) + 3])
    if (!early) {
      if (b < NFFN) mbar_wait(bar_box + (warp >> 1) * 8, 0);
      LOAD_WF(0);
      __syncwarp();
      mbar_arrive_pred(bar_gate, lane0);
    }
    if (b < NFFN) {
      const uint32_t own = base + unit_of(FT_G, warp >> 1) + (warp & 1) * 8192;
      mbar_wait(bar_box + (4 + (warp >> 1)) * 8, 0);
      LOAD_WF(1);
      uint32_t* const ydst = g_ypart + ((size_t)(warp * 16 + tq * 2) * NFFN + b) * 8 + g;
      PROF(8, ct == PT, 31); STAMP(10);
      bool wdok;
      {
        uint32_t n = 0;
        while (!(wdok = __all_sync(0xffffffffu, mbar_test(bar_box + (8 + (warp >> 1)) * 8, 0))) && !__all_sync(0xffffffffu, mbar_test(bar_sel, 0))) watchdog(n);
      }
      if (wdok) {
#pragma unroll
        for (int f = 0; f < 16; f++) LOAD_WD(f);
      }
      STAMP(11);
      mbar_wait(bar_sel, 0);
      PROF(8, ct == PT, 33); STAMP(12);
      float d[8][4];
#pragma unroll
      for (int i = 0; i < 4; i++) { d[i][0] = 0.f; d[i][1] = 0.f; d[i][2] = 0.f; d[i][3] = 0.f; }
#pragma unroll
      for (int ks = 0; ks < 8; ks++) {
        const uint2 hb = lds2(own + 256 + ks * 32 + tq * 8);
#pragma unroll
        for (int mt = 0; mt < 4; mt++) {
          const int r = ks * 16 + mt * 4;
          mma16816(d[mt], wf[r], wf[r + 1], wf[r + 2], wf[r + 3], hb.x, hb.y);
        }
      }
      sts2(own + (tq * 8 + g) * 8, __float_as_uint((tq & 2) ? ((tq & 1) ? d[1][2] : d[1][0]) : ((tq & 1) ? d[0][2] : d[0][0])),
           __float_as_uint((tq & 2) ? ((tq & 1) ? d[3][2] : d[3][0]) : ((tq & 1) ? d[2][2] : d[2][0])));
      bar_sync(1, 256);
      uint32_t ab[4];
      {
        float G = 0.f, U = 0.f;
        uint2 pv[8];
#pragma unroll
        for (int w8 = 0; w8 < 8; w8++) pv[w8] = lds2(base + ln * 8 + ((FT_G >> (w8 >> 1) * 4) & 15) * UNIT + (w8 & 1) * 8192);
#pragma unroll
        for (int w8 = 0; w8 < 8; w8 += 2) {
          G += __uint_as_float(pv[w8].x) + __uint_as_float(pv[w8 + 1].x);
          U += __uint_as_float(pv[w8].y) + __uint_as_float(pv[w8 + 1].y);
        }
        const float act = rbf(silu_f(rbf(G))) * rbf(U);
        const uint32_t pk = pack_bf(act, __shfl_down_sync(0xffffffffu, act, 1));
#pragma unroll
        for (int i = 0; i < 4; i++) ab[i] = __shfl_sync(0xffffffffu, pk, i * 8 + tq * 2);
      }
      if (!wdok) {
        mbar_wait(bar_box + (8 + (warp >> 1)) * 8, 0);
#pragma unroll
        for (int f = 0; f < 16; f++) LOAD_WD(f);
      }
      PROF(8, ct == PT, 34); STAMP(13);
#pragma unroll
      for (int mt = 0; mt < 8; mt++) {
        d[mt][0] = 0.f; d[mt][1] = 0.f; d[mt][2] = 0.f; d[mt][3] = 0.f;
        mma16816(d[mt], wd[mt * 8], wd[mt * 8 + 1], wd[mt * 8 + 2], wd[mt * 8 + 3], ab[0], ab[1]);
        mma16816(d[mt], wd[mt * 8 + 4], wd[mt * 8 + 5], wd[mt * 8 + 6], wd[mt * 8 + 7], ab[2], ab[3]);
      }
#pragma unroll
      for (int i = 0; i < 4; i++) {
        const int m4 = (i >> 1) * 4, e = (i & 1) * 2;
        const float y = (tq & 2) ? ((tq & 1) ? d[m4 + 3][e] : d[m4 + 2][e]) : ((tq & 1) ? d[m4 + 1][e] : d[m4][e]);
        st_relaxed(ydst + (m4 * 2 + (i & 1)) * NFFN * 8, tagf(y, tag));
      }
      PROF(8, ct == PT, 35); STAMP(14);
    }
    mbar_wait(bar_sel, 0);
    mbar_arrive_pred(bar_win, ct == 0);
    const int iwin = lds1(par + PAR_CONST + 60) & 0x7ff;
    const bool cand = (iwin >> 4) == rb * 8 + warp;
    {
      const uint32_t mm0 = __shfl_sync(0xffffffffu, mm, ln & ~1), mm1 = __shfl_sync(0xffffffffu, mm, ln | 1);
      const uint32_t ih0 = __shfl_sync(0xffffffffu, ih, ln & ~1), ih1 = __shfl_sync(0xffffffffu, ih, ln | 1);
      const uint32_t il0 = __shfl_sync(0xffffffffu, il, ln & ~1), il1 = __shfl_sync(0xffffffffu, il, ln | 1);
#pragma unroll 1
      for (int hf = 0; hf < 2; hf++) {
        uint32_t x[16];
#pragma unroll
        for (int i = 0; i < 8; i += 2) ldmatrix4((trow ^ (i << 4)) + hf * 16384, x[2 * i], x[2 * i + 1], x[2 * i + 2], x[2 * i + 3]);
#pragma unroll
        for (int i = 0; i < 8; i++) {
          const uint4 pv = lds4(par + PAR_T2 + (hf * 8 + i) * 64 + tq * 16);
          x[2 * i] = hadd2(x[2 * i], hmul2(pv.z, ln_mod(x[2 * i], mm0, ih0, il0, pv.x, pv.y)));
          x[2 * i + 1] = hadd2(x[2 * i + 1], hmul2(pv.z, ln_mod(x[2 * i + 1], mm1, ih1, il1, pv.x, pv.y)));
        }
#pragma unroll
        for (int i = 0; i < 8; i += 2) stmatrix4((trow ^ (i << 4)) + hf * 16384, x[2 * i], x[2 * i + 1], x[2 * i + 2], x[2 * i + 3]);
      }
      if (!cand) fence_async_smem();
      __syncwarp();
      if (!cand && elect_one()) {
        tma2d_store(&maps.out, res + warp * 2048, cj * 128, rb * 128 + warp * 16);
        tma2d_store(&maps.out, res + 16384 + warp * 2048, cj * 128 + 64, rb * 128 + warp * 16);
        asm volatile("cp.async.bulk.commit_group;" ::: "memory");
      }
    }
    if (cand) {
      const int wrow0 = warp * 16;
#pragma unroll 2
      for (int p = 0; p < 8; p++) {
        const int row = 2 * p + (ln >> 4), ch = ln & 15;
        const uint4 v = lds4(res + (ch >> 3) * 16384 + (wrow0 + row) * 128 + (((ch & 7) ^ (row & 7)) << 4));
        if (rb * 128 + wrow0 + row != iwin) *reinterpret_cast<uint4*>(P.out + (size_t)(rb * 128 + wrow0 + row) * DM + cj * 128 + ch * 8) = v;
      }
    }
    asm volatile("cp.async.bulk.wait_group.read 0;" ::: "memory");
    PROF(8, ct == PT, 11); STAMP(15);
    cluster_wait();
  }
}

typedef CUresult (*EncodeFn)(CUtensorMap*, CUtensorMapDataType, cuuint32_t, void*, const cuuint64_t*, const cuuint64_t*,
                             const cuuint32_t*, const cuuint32_t*, CUtensorMapInterleave, CUtensorMapSwizzle,
                             CUtensorMapL2promotion, CUtensorMapFloatOOBfill);

void map2d(EncodeFn enc, CUtensorMap* m, const void* p, uint64_t rows, uint64_t cols, uint32_t brows) {
  cuuint64_t dims[2] = {cols, rows}, strides[1] = {cols * 2};
  cuuint32_t box[2] = {64, brows}, es[2] = {1, 1};
  enc(m, CU_TENSOR_MAP_DATA_TYPE_BFLOAT16, 2, const_cast<void*>(p), dims, strides, box, es, CU_TENSOR_MAP_INTERLEAVE_NONE,
      CU_TENSOR_MAP_SWIZZLE_128B, CU_TENSOR_MAP_L2_PROMOTION_L2_256B, CU_TENSOR_MAP_FLOAT_OOB_FILL_NONE);
}
void map2d_narrow(EncodeFn enc, CUtensorMap* m, const void* p, uint64_t rows, uint64_t cols, uint32_t brows) {
  cuuint64_t dims[2] = {cols, rows}, strides[1] = {cols * 2};
  cuuint32_t box[2] = {32, brows}, es[2] = {1, 1};
  enc(m, CU_TENSOR_MAP_DATA_TYPE_BFLOAT16, 2, const_cast<void*>(p), dims, strides, box, es, CU_TENSOR_MAP_INTERLEAVE_NONE,
      CU_TENSOR_MAP_SWIZZLE_64B, CU_TENSOR_MAP_L2_PROMOTION_L2_64B, CU_TENSOR_MAP_FLOAT_OOB_FILL_NONE);
}
void map3d(EncodeFn enc, CUtensorMap* m, const void* p, uint64_t rows, uint64_t cols, uint32_t brows, uint32_t nch) {
  cuuint64_t dims[3] = {64, rows, cols / 64}, strides[2] = {cols * 2, 128};
  cuuint32_t box[3] = {64, brows, nch}, es[3] = {1, 1, 1};
  enc(m, CU_TENSOR_MAP_DATA_TYPE_BFLOAT16, 3, const_cast<void*>(p), dims, strides, box, es, CU_TENSOR_MAP_INTERLEAVE_NONE,
      CU_TENSOR_MAP_SWIZZLE_128B, CU_TENSOR_MAP_L2_PROMOTION_L2_256B, CU_TENSOR_MAP_FLOAT_OOB_FILL_NONE);
}

}

extern "C" void kernel_launch(void* const* d_in, const int* in_sizes, int n_in, void* d_out, int out_size) {
  (void)in_sizes; (void)n_in; (void)out_size;
  static EncodeFn enc = nullptr;
  if (!enc) {
    void* fn = nullptr;
    cudaDriverEntryPointQueryResult st;
    cudaGetDriverEntryPoint("cuTensorMapEncodeTiled", &fn, cudaEnableDefault, &st);
    enc = (EncodeFn)fn;
    cudaFuncSetAttribute(fused_kernel, cudaFuncAttributeMaxDynamicSharedMemorySize, SMEM_BYTES);
  }
  Maps maps;
  map2d(enc, &maps.x, d_in[0], SEQ, DM, 128);
  map2d(enc, &maps.out, d_out, SEQ, DM, 16);
  map3d(enc, &maps.wq, d_in[3], DM, NQ, 64, 2);
  map3d(enc, &maps.k, d_in[1], 4 * SK, 128, 128, 1);
  map3d(enc, &maps.v, d_in[2], 4 * SK, 128, 128, 1);
  map3d(enc, &maps.wo, d_in[4], NQ, DM, 64, 2);
  map2d_narrow(enc, &maps.wg, d_in[7], DM, FF, 256);
  map2d_narrow(enc, &maps.wu, d_in[8], DM, FF, 256);
  map3d(enc, &maps.wd, d_in[9], FF, DM, 32, 4);
  map2d_narrow(enc, &maps.wm, d_in[11], DM, NMOD, 256);
  Ptrs p;
  p.x = (const __nv_bfloat16*)d_in[0];
  p.w_r = (const __nv_bfloat16*)d_in[6];
  p.w_gate = (const __nv_bfloat16*)d_in[7];
  p.w_up = (const __nv_bfloat16*)d_in[8];
  p.w_down = (const __nv_bfloat16*)d_in[9];
  p.c = (const __nv_bfloat16*)d_in[10];
  p.w_mod = (const __nv_bfloat16*)d_in[11];
  p.out = (__nv_bfloat16*)d_out;
  fused_kernel<<<NMAIN + NHELP, 384, SMEM_BYTES>>>(maps, p);
}
```

```cpp
#include <cuda_runtime.h>
#include <cuda_bf16.h>
#include <cuda.h>
#include <stdint.h>
#include <type_traits>

#define HD 2
#define HDX 2
#define NRS 8
#define FPACE 3
#define GOST 20
#define WB 2
#define WN 20
#define RES0 17
#define RES1 20
#define HU 32
#define NS1 5
#define PG0 15
#define PSL 0
#define FB0 0
#define FB2 8
#define OPS 8192
#define OFL 0
#define ODS 8
#define MODUL hfma2
#define ODS1 5
#define LD1 0
#define LD2 4
#define FB1 2
#define FPB 8
#define FPACE0 2
#define HWB 0
#define GLATE 0
#define VREL 5
#define E0 3

namespace {

constexpr int SEQ = 2048, DM = 1024, NQ = 4096, SK = 2048, WIN = 512, FF = 3584, NMOD = 6144;
constexpr int NMAIN = 128, NHELP = 4, NFFN = 112;
constexpr int NSLOT = 4, SLOT_BYTES = 32768, UNIT = 16384, GST_BYTES = 3 * UNIT;
constexpr uint32_t XT1 = 0xDCBA, XT2 = 0x9687;
constexpr uint32_t WT0 = 0xA741, WT1 = 0x7420, WT2 = 0x4A20;
constexpr uint32_t AT0 = WT1, AT1 = WT2;
constexpr uint32_t QT = 0xDC9696DC;
constexpr int OFF_STAGE = 12 * UNIT;
constexpr uint32_t FT_G = 0x07B3, FT_U = 0xA628, FT_D = 0x5149;
constexpr int OFF_RES = 12 * UNIT;
constexpr int OFF_PAR = 14 * UNIT;
constexpr int OFF_BAR = OFF_PAR + 2520;
constexpr int SMEM_BYTES = OFF_BAR + 552;
static_assert(SMEM_BYTES <= 232448, "smem");

constexpr int PAR_T1 = 0;
constexpr int PAR_T2 = 512;
constexpr int PAR_CONST = 1536;
constexpr int PAR_RED = 1600;
constexpr int PAR_SINK = 2176;

struct Maps {
  CUtensorMap x, wq, k, v, wo, wg, wu, wd, wm, out;
};
struct Ptrs {
  const __nv_bfloat16 *x, *w_r, *c, *w_mod, *w_gate, *w_up, *w_down;
  __nv_bfloat16* out;
};

__device__ __align__(1024) uint8_t g_act[16 * 80 * UNIT];
__device__ __align__(128) uint32_t g_mod[NMOD];
__device__ __align__(128) uint32_t g_modp[2 * 2 * DM];
__device__ __align__(128) uint32_t g_ln1[SEQ * 4];
__device__ __align__(128) uint32_t g_cnt_h[16 * 32];
__device__ __align__(128) uint32_t g_cnt_o[128 * 32];
__device__ __align__(128) uint32_t g_xch[NMAIN * 8 * 256 * 4];
__device__ __align__(128) uint32_t g_stats[8 * SEQ * 4];
__device__ __align__(128) uint32_t g_cand[32];
__device__ __align__(128) uint32_t g_row[16 * 2 * DM];
__device__ __align__(128) uint32_t g_ypart[NMAIN * NFFN * 8];
__device__ uint32_t g_epoch;

__device__ __forceinline__ uint32_t fresh_lane() { uint32_t l; asm volatile("mov.u32 %0, %%laneid;" : "=r"(l)); return l; }
__device__ __forceinline__ uint32_t frag_offset(int warp) {
  const uint32_t l = fresh_lane();
  return ((warp & 3) * 16 + (l & 15)) * 128 + (((l >> 4) ^ (l & 7)) << 4);
}
__device__ __forceinline__ bool elect_one() {
  uint32_t p;
  asm volatile("{ .reg .pred q; elect.sync _|q, 0xffffffff; selp.u32 %0, 1, 0, q; }" : "=r"(p));
  return p;
}
__device__ __forceinline__ uint32_t smem_u32(const void* p) { return (uint32_t)__cvta_generic_to_shared(p); }
__device__ __forceinline__ void mbar_init(uint32_t bar, uint32_t cnt) {
  asm volatile("mbarrier.init.shared::cta.b64 [%0], %1;" ::"r"(bar), "r"(cnt) : "memory");
}
__device__ __forceinline__ void mbar_expect_tx(uint32_t bar, uint32_t bytes) {
  asm volatile("mbarrier.arrive.expect_tx.shared::cta.b64 _, [%0], %1;" ::"r"(bar), "r"(bytes) : "memory");
}
__device__ __forceinline__ void mbar_arrive(uint32_t bar) {
  asm volatile("mbarrier.arrive.shared::cta.b64 _, [%0];" ::"r"(bar) : "memory");
}
__device__ __forceinline__ void mbar_arrive_pred(uint32_t bar, bool p) {
  asm volatile("{ .reg .pred p; setp.ne.b32 p, %1, 0; @p mbarrier.arrive.shared::cta.b64 _, [%0]; }" ::"r"(bar), "r"((int)p) : "memory");
}
__device__ __forceinline__ void mbar_arrive_cl(uint32_t bar, uint32_t off, bool p = true) {
  asm volatile("{ .reg .pred p, q; .reg .b32 a; setp.ne.b32 q, %2, 0; setp.ne.and.b32 p, %0, 0, q; add.u32 a, %0, %1; @p mbarrier.arrive.shared::cluster.b64 _, [a]; }"
               ::"r"(bar), "r"(off), "r"((int)p) : "memory");
}
__device__ __forceinline__ uint32_t mapa(uint32_t addr, uint32_t cta) {
  uint32_t r; asm("mapa.shared::cluster.u32 %0, %1, %2;" : "=r"(r) : "r"(addr), "r"(cta)); return r;
}
__device__ __forceinline__ void cluster_arrive() { asm volatile("barrier.cluster.arrive.relaxed.aligned;" ::: "memory"); }
__device__ __forceinline__ void cluster_wait() { asm volatile("barrier.cluster.wait.aligned;" ::: "memory"); }
__device__ __forceinline__ void watchdog(uint32_t& n) {
}
__device__ __forceinline__ void mbar_wait(uint32_t bar, uint32_t parity) {
  asm volatile("{\n.reg .pred p;\nWAIT_%=:\nmbarrier.try_wait.parity.shared::cta.b64 p, [%0], %1;\n@!p bra WAIT_%=;\n}" ::"r"(bar), "r"(parity) : "memory");
}
__device__ __forceinline__ bool mbar_test(uint32_t bar, uint32_t parity) {
  uint32_t ok;
  asm volatile("{\n.reg .pred p;\nmbarrier.test_wait.parity.shared::cta.b64 p, [%1], %2;\nselp.u32 %0, 1, 0, p;\n}" : "=r"(ok) : "r"(bar), "r"(parity) : "memory");
  return ok;
}
__device__ __forceinline__ uint64_t l2_stream() {
  uint64_t f; asm("createpolicy.fractional.L2::evict_first.b64 %0, 1.0;" : "=l"(f)); return f;
}
__device__ __forceinline__ void tma2d(uint32_t dst, const CUtensorMap* m, int c0, int c1, uint32_t bar) {
  asm volatile("cp.async.bulk.tensor.2d.shared::cluster.global.mbarrier::complete_tx::bytes.L2::cache_hint [%0], [%1, {%3, %4}], [%2], %5;"
               ::"r"(dst), "l"(m), "r"(bar), "r"(c0), "r"(c1), "l"(l2_stream()) : "memory");
}
__device__ __forceinline__ void bulk_load(uint32_t dst, const void* src, uint32_t bytes, uint32_t bar) {
  asm volatile("cp.async.bulk.shared::cluster.global.mbarrier::complete_tx::bytes [%0], [%1], %2, [%3];" ::"r"(dst), "l"(src), "r"(bytes), "r"(bar) : "memory");
}
__device__ __forceinline__ void bulk_load_stream(uint32_t dst, const void* src, uint32_t bytes, uint32_t bar) {
  asm volatile("cp.async.bulk.shared::cluster.global.mbarrier::complete_tx::bytes.L2::cache_hint [%0], [%1], %2, [%3], %4;"
               ::"r"(dst), "l"(src), "r"(bytes), "r"(bar), "l"(l2_stream()) : "memory");
}
__device__ __forceinline__ void tma2d_store(const CUtensorMap* m, uint32_t src, int c0, int c1) {
  asm volatile("cp.async.bulk.tensor.2d.global.shared::cta.bulk_group [%0, {%2, %3}], [%1];" ::"l"(m), "r"(src), "r"(c0), "r"(c1) : "memory");
}
__device__ __forceinline__ void bulk_store(void* dst, uint32_t src, uint32_t bytes) {
  asm volatile("cp.async.bulk.global.shared::cta.bulk_group [%0], [%1], %2;" ::"l"(dst), "r"(src), "r"(bytes) : "memory");
}
__device__ __forceinline__ int slice_of(int i) { return i + ((i & 7) == 1) - ((i & 7) == 2); }
__device__ __forceinline__ uint32_t unit_of(uint32_t table, uint32_t i) { return ((table >> (i * 4)) & 15) * UNIT; }
__device__ __forceinline__ void tma3d(uint32_t dst, const CUtensorMap* m, int c0, int c1, int c2, uint32_t bar) {
  asm volatile("cp.async.bulk.tensor.3d.shared::cluster.global.mbarrier::complete_tx::bytes.L2::cache_hint [%0], [%1, {%3, %4, %5}], [%2], %6;"
               ::"r"(dst), "l"(m), "r"(bar), "r"(c0), "r"(c1), "r"(c2), "l"(l2_stream()) : "memory");
}
template <bool STREAM>
__device__ __forceinline__ void tma3d_mc(uint32_t dst, const CUtensorMap* m, int c0, int c1, int c2, uint32_t bar) {
  if (STREAM)
    asm volatile("cp.async.bulk.tensor.3d.shared::cluster.global.mbarrier::complete_tx::bytes.multicast::cluster.L2::cache_hint [%0], [%1, {%3, %4, %5}], [%2], %6, %7;"
                 ::"r"(dst), "l"(m), "r"(bar), "r"(c0), "r"(c1), "r"(c2), "h"((uint16_t)3), "l"(l2_stream()) : "memory");
  else
    asm volatile("cp.async.bulk.tensor.3d.shared::cluster.global.mbarrier::complete_tx::bytes.multicast::cluster [%0], [%1, {%3, %4, %5}], [%2], %6;"
                 ::"r"(dst), "l"(m), "r"(bar), "r"(c0), "r"(c1), "r"(c2), "h"((uint16_t)3) : "memory");
}
__device__ __forceinline__ void prefetch_map(const CUtensorMap* m) {
  asm volatile("prefetch.tensormap [%0];" ::"l"(m) : "memory");
}
__device__ __forceinline__ void fence_async() { asm volatile("fence.proxy.async.global;" ::: "memory"); }
__device__ __forceinline__ void fence_async_smem() { asm volatile("fence.proxy.async.shared::cta;" ::: "memory"); }
__device__ __forceinline__ void bar_sync(int id, int n) { asm volatile("bar.sync %0, %1;" ::"r"(id), "r"(n) : "memory"); }
__device__ __forceinline__ void bar_arrive(int id, int n) { asm volatile("bar.arrive %0, %1;" ::"r"(id), "r"(n) : "memory"); }
__device__ __forceinline__ void wg_fence() { asm volatile("wgmma.fence.sync.aligned;" ::: "memory"); }
__device__ __forceinline__ void wg_commit() { asm volatile("wgmma.commit_group.sync.aligned;" ::: "memory"); }
template <int N> __device__ __forceinline__ void wg_wait() { asm volatile("wgmma.wait_group.sync.aligned %0;" ::"n"(N) : "memory"); }
__device__ __forceinline__ uint64_t make_desc(uint32_t addr, uint32_t lbo, uint32_t sbo) {
  return (uint64_t)((addr & 0x3FFFF) >> 4) | ((uint64_t)(lbo >> 4) << 16) | ((uint64_t)(sbo >> 4) << 32) | (1ull << 62);
}
__device__ __forceinline__ uint32_t ld_relaxed(const uint32_t* p) {
  uint32_t v; asm volatile("ld.relaxed.gpu.global.u32 %0, [%1];" : "=r"(v) : "l"(p) : "memory"); return v;
}
__device__ __forceinline__ uint32_t ld_acquire(const uint32_t* p) {
  uint32_t v; asm volatile("ld.acquire.gpu.global.u32 %0, [%1];" : "=r"(v) : "l"(p) : "memory"); return v;
}
__device__ __forceinline__ uint4 ld_relaxed4(const uint32_t* p) {
  uint4 v; asm volatile("ld.relaxed.gpu.global.v4.u32 {%0,%1,%2,%3}, [%4];" : "=r"(v.x), "=r"(v.y), "=r"(v.z), "=r"(v.w) : "l"(p) : "memory"); return v;
}
__device__ __forceinline__ uint2 ld_relaxed2(const uint32_t* p) {
  uint2 v; asm volatile("ld.relaxed.gpu.global.v2.u32 {%0,%1}, [%2];" : "=r"(v.x), "=r"(v.y) : "l"(p) : "memory"); return v;
}
__device__ __forceinline__ void st_relaxed(uint32_t* p, uint32_t v) {
  asm volatile("st.relaxed.gpu.global.u32 [%0], %1;" ::"l"(p), "r"(v) : "memory");
}
__device__ __forceinline__ void st_relaxed2(uint32_t* p, uint32_t a, uint32_t b) {
  asm volatile("st.relaxed.gpu.global.v2.u32 [%0], {%1,%2};" ::"l"(p), "r"(a), "r"(b) : "memory");
}
__device__ __forceinline__ void st_relaxed4(uint32_t* p, uint32_t a, uint32_t b, uint32_t c, uint32_t d) {
  asm volatile("st.relaxed.gpu.global.v4.u32 [%0], {%1,%2,%3,%4};" ::"l"(p), "r"(a), "r"(b), "r"(c), "r"(d) : "memory");
}
__device__ __forceinline__ void st_b128(uint32_t* p, uint32_t a, uint32_t b, uint32_t c, uint32_t d) {
  asm volatile("{ .reg .b64 u, v; .reg .b128 w; mov.b64 u, {%1, %2}; mov.b64 v, {%3, %4}; mov.b128 w, {u, v}; st.relaxed.gpu.global.b128 [%0], w; }"
               ::"l"(p), "r"(a), "r"(b), "r"(c), "r"(d) : "memory");
}
__device__ __forceinline__ uint4 ld_b128(const uint32_t* p) {
  uint4 r;
  asm volatile("{ .reg .b64 u, v; .reg .b128 w; ld.relaxed.gpu.global.b128 w, [%4]; mov.b128 {u, v}, w; mov.b64 {%0, %1}, u; mov.b64 {%2, %3}, v; }"
               : "=r"(r.x), "=r"(r.y), "=r"(r.z), "=r"(r.w) : "l"(p) : "memory");
  return r;
}
__device__ __forceinline__ void st_pairs(uint32_t* p, uint32_t a, uint32_t b, uint32_t tag) {
  asm volatile("{ .reg .b64 u, v; mov.b64 u, {%1, %3}; mov.b64 v, {%2, %3}; st.relaxed.gpu.global.v2.b64 [%0], {u, v}; }"
               ::"l"(p), "r"(a), "r"(b), "r"(tag) : "memory");
}
__device__ __forceinline__ uint4 ld_pairs(const uint32_t* p) {
  uint4 v;
  asm volatile("{ .reg .b64 u, v; ld.relaxed.gpu.global.v2.b64 {u, v}, [%4]; mov.b64 {%0, %1}, u; mov.b64 {%2, %3}, v; }"
               : "=r"(v.x), "=r"(v.y), "=r"(v.z), "=r"(v.w) : "l"(p) : "memory");
  return v;
}
__device__ __forceinline__ uint2 ld_pair(const uint32_t* p) {
  uint2 v;
  asm volatile("{ .reg .b64 u; ld.relaxed.gpu.global.b64 u, [%2]; mov.b64 {%0, %1}, u; }" : "=r"(v.x), "=r"(v.y) : "l"(p) : "memory");
  return v;
}
__device__ __forceinline__ void red_release(uint32_t* p, uint32_t v) {
  asm volatile("red.release.gpu.global.add.u32 [%0], %1;" ::"l"(p), "r"(v) : "memory");
}
__device__ __forceinline__ uint32_t ldg_nc1(const void* p) {
  uint32_t v;
  asm volatile("ld.global.nc.u32 %0, [%1];" : "=r"(v) : "l"(p));
  return v;
}
__device__ __forceinline__ uint4 ldg_nc4(const void* p) {
  uint4 v; asm volatile("ld.global.nc.L1::no_allocate.v4.u32 {%0,%1,%2,%3}, [%4];" : "=r"(v.x), "=r"(v.y), "=r"(v.z), "=r"(v.w) : "l"(p)); return v;
}
__device__ __forceinline__ uint4 ldg_stream4(const void* p) {
  uint4 v;
  asm volatile("ld.global.nc.L1::no_allocate.L2::cache_hint.v4.u32 {%0,%1,%2,%3}, [%4], %5;" : "=r"(v.x), "=r"(v.y), "=r"(v.z), "=r"(v.w) : "l"(p), "l"(l2_stream()));
  return v;
}
__device__ __forceinline__ void stg4(void* p, uint4 v) {
  asm volatile("st.global.v4.u32 [%0], {%1,%2,%3,%4};" ::"l"(p), "r"(v.x), "r"(v.y), "r"(v.z), "r"(v.w) : "memory");
}
__device__ __forceinline__ void wait_counter(const uint32_t* p, uint32_t target) {
  uint32_t n = 0;
  while (__any_sync(0xffffffffu, (int)(ld_acquire(p) - target) < 0)) { watchdog(n); }
}
__device__ __forceinline__ uint32_t tagf(float v, uint32_t tag) { return (__float_as_uint(v) & ~3u) | tag; }
__device__ __forceinline__ bool tag_ok(uint4 v, uint32_t tag) { return (((v.x ^ tag) | (v.y ^ tag) | (v.z ^ tag) | (v.w ^ tag)) & 3u) == 0; }
__device__ __forceinline__ float untag_sum(uint32_t a, uint32_t b) { return __uint_as_float(a & ~3u) + __uint_as_float(b & ~3u); }
__device__ __forceinline__ uint4 poll4(const uint32_t* p, uint32_t tag) {
  uint4 v = ld_relaxed4(p);
  uint32_t n = 0;
  while (!__all_sync(0xffffffffu, tag_ok(v, tag))) { v = ld_relaxed4(p); watchdog(n); }
  return v;
}
__device__ __forceinline__ float bf_lo(uint32_t v) { return __uint_as_float(v << 16); }
__device__ __forceinline__ float bf_hi(uint32_t v) { return __uint_as_float(v & 0xffff0000u); }
__device__ __forceinline__ uint32_t pack_bf(float lo, float hi) {
  uint32_t r; asm("cvt.rn.bf16x2.f32 %0, %1, %2;" : "=r"(r) : "f"(hi), "f"(lo)); return r;
}
__device__ __forceinline__ float rbf(float v) { return __uint_as_float(pack_bf(0.f, v) & 0xffff0000u); }
__device__ __forceinline__ uint32_t hmul2(uint32_t a, uint32_t b) {
  uint32_t r; asm("mul.rn.bf16x2 %0, %1, %2;" : "=r"(r) : "r"(a), "r"(b)); return r;
}
__device__ __forceinline__ uint32_t hadd2(uint32_t a, uint32_t b) {
  uint32_t r; asm("add.rn.bf16x2 %0, %1, %2;" : "=r"(r) : "r"(a), "r"(b)); return r;
}
__device__ __forceinline__ uint32_t hsub2(uint32_t a, uint32_t b) {
  uint32_t r; asm("sub.rn.bf16x2 %0, %1, %2;" : "=r"(r) : "r"(a), "r"(b)); return r;
}
__device__ __forceinline__ uint32_t hmax2(uint32_t a, uint32_t b) {
  uint32_t r; asm("max.bf16x2 %0, %1, %2;" : "=r"(r) : "r"(a), "r"(b)); return r;
}
__device__ __forceinline__ float rcp(float x) { float r; asm("rcp.approx.ftz.f32 %0, %1;" : "=f"(r) : "f"(x)); return r; }
__device__ __forceinline__ float ex2(float x) { float r; asm("ex2.approx.ftz.f32 %0, %1;" : "=f"(r) : "f"(x)); return r; }
__device__ __forceinline__ void stmatrix4(uint32_t addr, uint32_t a, uint32_t b, uint32_t c, uint32_t d) {
  asm volatile("stmatrix.sync.aligned.m8n8.x4.shared.b16 [%0], {%1,%2,%3,%4};" ::"r"(addr), "r"(a), "r"(b), "r"(c), "r"(d) : "memory");
}
__device__ __forceinline__ void ldmatrix4(uint32_t addr, uint32_t& a, uint32_t& b, uint32_t& c, uint32_t& d) {
  asm volatile("ldmatrix.sync.aligned.m8n8.x4.shared.b16 {%0,%1,%2,%3}, [%4];" : "=r"(a), "=r"(b), "=r"(c), "=r"(d) : "r"(addr) : "memory");
}
__device__ __forceinline__ void ldmatrix4t(uint32_t addr, uint32_t& a, uint32_t& b, uint32_t& c, uint32_t& d) {
  asm volatile("ldmatrix.sync.aligned.m8n8.x4.trans.shared.b16 {%0,%1,%2,%3}, [%4];" : "=r"(a), "=r"(b), "=r"(c), "=r"(d) : "r"(addr) : "memory");
}
__device__ __forceinline__ void mma16816(float (&d)[4], uint32_t a0, uint32_t a1, uint32_t a2, uint32_t a3, uint32_t b0, uint32_t b1) {
  asm volatile("mma.sync.aligned.m16n8k16.row.col.f32.bf16.bf16.f32 {%0,%1,%2,%3}, {%4,%5,%6,%7}, {%8,%9}, {%0,%1,%2,%3};"
               : "+f"(d[0]), "+f"(d[1]), "+f"(d[2]), "+f"(d[3]) : "r"(a0), "r"(a1), "r"(a2), "r"(a3), "r"(b0), "r"(b1));
}
__device__ __forceinline__ void sts1(uint32_t a, uint32_t v) { asm volatile("st.shared.u32 [%0], %1;" ::"r"(a), "r"(v) : "memory"); }
__device__ __forceinline__ uint4 lds4(uint32_t a) {
  uint4 v; asm volatile("ld.shared.v4.u32 {%0,%1,%2,%3}, [%4];" : "=r"(v.x), "=r"(v.y), "=r"(v.z), "=r"(v.w) : "r"(a) : "memory"); return v;
}
__device__ __forceinline__ uint2 lds2(uint32_t a) {
  uint2 v; asm volatile("ld.shared.v2.u32 {%0,%1}, [%2];" : "=r"(v.x), "=r"(v.y) : "r"(a) : "memory"); return v;
}
__device__ __forceinline__ uint32_t lds1(uint32_t a) {
  uint32_t v; asm volatile("ld.shared.u32 %0, [%1];" : "=r"(v) : "r"(a) : "memory"); return v;
}
__device__ __forceinline__ void sts2(uint32_t a, uint32_t x, uint32_t y) { asm volatile("st.shared.v2.u32 [%0], {%1,%2};" ::"r"(a), "r"(x), "r"(y) : "memory"); }
__device__ __forceinline__ void sts4(uint32_t a, uint4 v) {
  asm volatile("st.shared.v4.u32 [%0], {%1,%2,%3,%4};" ::"r"(a), "r"(v.x), "r"(v.y), "r"(v.z), "r"(v.w) : "memory");
}
__device__ __forceinline__ float silu_f(float v) { return __fdividef(v, 1.f + __expf(-v)); }
__device__ __forceinline__ uint32_t hfma2(uint32_t a, uint32_t b, uint32_t c) {
  uint32_t r; asm("fma.rn.bf16x2 %0, %1, %2, %3;" : "=r"(r) : "r"(a), "r"(b), "r"(c)); return r;
}
__device__ __forceinline__ void split_inv(float sd, uint32_t& ih, uint32_t& il) {
  const float inv = rcp(sd);
  ih = pack_bf(inv, inv);
  const float lo = inv - bf_lo(ih);
  il = pack_bf(lo, lo);
}
__device__ __forceinline__ uint32_t ln_norm(uint32_t x, uint32_t mean2, uint32_t ih, uint32_t il) {
  const uint32_t d = hsub2(x, mean2);
  return hfma2(d, ih, hmul2(d, il));
}
__device__ __forceinline__ uint32_t modul(uint32_t n, uint32_t c1, uint32_t sh) { return hadd2(hmul2(n, c1), sh); }
__device__ __forceinline__ uint32_t ln_mod(uint32_t x, uint32_t mean2, uint32_t ih, uint32_t il, uint32_t c1, uint32_t sh) {
  return modul(ln_norm(x, mean2, ih, il), c1, sh);
}

#define R8(a, i) "+f"(a[i]), "+f"(a[i + 1]), "+f"(a[i + 2]), "+f"(a[i + 3]), "+f"(a[i + 4]), "+f"(a[i + 5]), "+f"(a[i + 6]), "+f"(a[i + 7])
#define D64 "{%0,%1,%2,%3,%4,%5,%6,%7,%8,%9,%10,%11,%12,%13,%14,%15,%16,%17,%18,%19,%20,%21,%22,%23,%24,%25,%26,%27,%28,%29,%30,%31," \
            "%32,%33,%34,%35,%36,%37,%38,%39,%40,%41,%42,%43,%44,%45,%46,%47,%48,%49,%50,%51,%52,%53,%54,%55,%56,%57,%58,%59,%60,%61,%62,%63}"
template <int TB>
__device__ __forceinline__ void mma_ss(float (&d)[64], uint64_t da, uint64_t db, int sc) {
  asm volatile("{\n.reg .pred p;\nsetp.ne.b32 p, %66, 0;\n"
               "wgmma.mma_async.sync.aligned.m64n128k16.f32.bf16.bf16 " D64 ", %64, %65, p, 1, 1, 0, %67;\n}"
               : R8(d, 0), R8(d, 8), R8(d, 16), R8(d, 24), R8(d, 32), R8(d, 40), R8(d, 48), R8(d, 56)
               : "l"(da), "l"(db), "r"(sc), "n"(TB));
}
template <int TB>
__device__ __forceinline__ void mma_rs(float (&d)[64], uint32_t a0, uint32_t a1, uint32_t a2, uint32_t a3, uint64_t db, int sc) {
  asm volatile("{\n.reg .pred p;\nsetp.ne.b32 p, %69, 0;\n"
               "wgmma.mma_async.sync.aligned.m64n128k16.f32.bf16.bf16 " D64 ", {%64,%65,%66,%67}, %68, p, 1, 1, %70;\n}"
               : R8(d, 0), R8(d, 8), R8(d, 16), R8(d, 24), R8(d, 32), R8(d, 40), R8(d, 48), R8(d, 56)
               : "r"(a0), "r"(a1), "r"(a2), "r"(a3), "l"(db), "r"(sc), "n"(TB));
}
#define D128 "{%0,%1,%2,%3,%4,%5,%6,%7,%8,%9,%10,%11,%12,%13,%14,%15,%16,%17,%18,%19,%20,%21,%22,%23,%24,%25,%26,%27,%28,%29,%30,%31," \
             "%32,%33,%34,%35,%36,%37,%38,%39,%40,%41,%42,%43,%44,%45,%46,%47,%48,%49,%50,%51,%52,%53,%54,%55,%56,%57,%58,%59,%60,%61,%62,%63," \
             "%64,%65,%66,%67,%68,%69,%70,%71,%72,%73,%74,%75,%76,%77,%78,%79,%80,%81,%82,%83,%84,%85,%86,%87,%88,%89,%90,%91,%92,%93,%94,%95," \
             "%96,%97,%98,%99,%100,%101,%102,%103,%104,%105,%106,%107,%108,%109,%110,%111,%112,%113,%114,%115,%116,%117,%118,%119,%120,%121,%122,%123,%124,%125,%126,%127}"
#define R128(d, e) R8(d, 0), R8(d, 8), R8(d, 16), R8(d, 24), R8(d, 32), R8(d, 40), R8(d, 48), R8(d, 56), \
                   R8(e, 0), R8(e, 8), R8(e, 16), R8(e, 24), R8(e, 32), R8(e, 40), R8(e, 48), R8(e, 56)
__device__ __forceinline__ void mma256_ss(float (&d)[64], float (&e)[64], uint64_t da, uint64_t db, int sc) {
  asm volatile("{\n.reg .pred p;\nsetp.ne.b32 p, %130, 0;\n"
               "wgmma.mma_async.sync.aligned.m64n256k16.f32.bf16.bf16 " D128 ", %128, %129, p, 1, 1, 0, 1;\n}"
               : R128(d, e) : "l"(da), "l"(db), "r"(sc));
}
__device__ __forceinline__ void mma256_rs(float (&d)[64], float (&e)[64], uint32_t a0, uint32_t a1, uint32_t a2, uint32_t a3, uint64_t db) {
  asm volatile("{\n.reg .pred p;\nsetp.ne.b32 p, 1, 0;\n"
               "wgmma.mma_async.sync.aligned.m64n256k16.f32.bf16.bf16 " D128 ", {%128,%129,%130,%131}, %132, p, 1, 1, 1;\n}"
               : R128(d, e) : "r"(a0), "r"(a1), "r"(a2), "r"(a3), "l"(db));
}
template <int N> __device__ __forceinline__ void keep(float (&a)[N]) {
#pragma unroll
  for (int i = 0; i < N; i++) asm volatile("" : "+f"(a[i])::"memory");
}
template <int N> __device__ __forceinline__ void keep(uint32_t (&a)[N]) {
#pragma unroll
  for (int i = 0; i < N; i++) asm volatile("" : "+r"(a[i])::"memory");
}

#define STAMP(idx) do {} while (0)
#define PROF(grp, cond, idx) do {} while (0)

constexpr float SCL2 = 1.4426950408889634f * 0.08838834764831845f;

__device__ __forceinline__ void pack_p(const float (&s)[64], uint32_t (&p)[32]) {
#pragma unroll
  for (int i = 0; i < 32; i++) p[i] = pack_bf(s[2 * i], s[2 * i + 1]);
}

__device__ __forceinline__ void issue_qk(float (&s)[64], uint32_t q0, uint32_t q1, uint32_t kslot) {
  const uint64_t db = make_desc(kslot, 16, 1024), da0 = make_desc(q0, 16, 1024), da1 = make_desc(q1, 16, 1024);
#pragma unroll
  for (int kk = 0; kk < 8; kk++) mma_ss<0>(s, (kk < 4 ? da0 : da1) + (kk & 3) * 2, db + (kk >> 2) * 1024 + (kk & 3) * 2, kk != 0);
}
__device__ __forceinline__ void issue_pv(float (&o)[64], uint32_t (&p)[32], uint32_t vslot, int acc) {
  uint64_t db = make_desc(vslot, 16384, 1024);
#pragma unroll
  for (int kk = 0; kk < 8; kk++)
    mma_rs<1>(o, p[4 * kk], p[4 * kk + 1], p[4 * kk + 2], p[4 * kk + 3], db + kk * 128, kk == 0 ? acc : 1);
}

template <int H>
__device__ __forceinline__ void store_chunk(const float (&a)[64], uint32_t addr) {
#pragma unroll
  for (int i = 8 * H; i < 8 * H + 8; i += 2)
    stmatrix4(addr ^ ((i & 7) << 4), pack_bf(a[4 * i], a[4 * i + 1]), pack_bf(a[4 * i + 2], a[4 * i + 3]),
              pack_bf(a[4 * i + 4], a[4 * i + 5]), pack_bf(a[4 * i + 6], a[4 * i + 7]));
}
template <int H>
__device__ __forceinline__ void store_chunk(const float (&a)[64], float i0, float i1, uint32_t addr) {
#pragma unroll
  for (int i = 8 * H; i < 8 * H + 8; i += 2)
    stmatrix4(addr ^ ((i & 7) << 4), pack_bf(a[4 * i] * i0, a[4 * i + 1] * i0), pack_bf(a[4 * i + 2] * i1, a[4 * i + 3] * i1),
              pack_bf(a[4 * i + 4] * i0, a[4 * i + 5] * i0), pack_bf(a[4 * i + 6] * i1, a[4 * i + 7] * i1));
}
__device__ __forceinline__ float inv_quad_sum(float l) {
  l += __shfl_xor_sync(0xffffffffu, l, 1);
  l += __shfl_xor_sync(0xffffffffu, l, 2);
  return rcp(l);
}

__device__ __forceinline__ void write_table(uint32_t table, bool ca, uint32_t t, const uint4& m0, const uint4& m1) {
  float c0 = untag_sum(m0.x, m1.x), c1 = untag_sum(m0.y, m1.y), c2 = untag_sum(m0.z, m1.z), c3 = untag_sum(m0.w, m1.w);
  if (ca) { c0 = 1.f + rbf(c0); c1 = 1.f + rbf(c1); c2 = 1.f + rbf(c2); c3 = 1.f + rbf(c3); }
  const uint32_t d = table + (t >> 2) * 64 + (t & 1) * 32 + (t & 2) * 2 + (ca ? 0 : 8);
  sts1(d, pack_bf(c0, c1));
  sts1(d + 16, pack_bf(c2, c3));
}

__device__ __forceinline__ void ln_scalars(float mean, float var, float& mb, float& sd) {
  mb = rbf(mean);
  float r; asm("sqrt.approx.ftz.f32 %0, %1;" : "=f"(r) : "f"(rbf(rbf(var) + 1e-5f)));
  sd = rbf(r);
}

__global__ void __cluster_dims__(2, 1, 1) __launch_bounds__(384, 1) fused_kernel(const __grid_constant__ Maps maps, const Ptrs P) {
  extern __shared__ __align__(1024) uint8_t smem_raw[];
  const uint32_t base = smem_u32(smem_raw);
  const int tid = threadIdx.x, lane = tid & 31;
  const int warp = __shfl_sync(0xffffffffu, tid >> 5, 0);
  const int b = blockIdx.x;
  PROF(31, tid == 0, 0);

  if (b >= NMAIN) {
    float* sc = reinterpret_cast<float*>(smem_raw);
    float* red = sc + DM;
    for (int k = tid; k < DM; k += 384) sc[k] = rbf(silu_f(__bfloat162float(P.c[k])));
    __syncthreads();
    if (tid < 256) {
      const int col = 2048 + (b - NMAIN) * 1024 + (tid & 127) * 8, r0 = (tid >> 7) * 512;
      float acc[8];
#pragma unroll
      for (int e = 0; e < 8; e++) acc[e] = 0.f;
#pragma unroll 1
      for (int r = r0; r < r0 + 512; r += HU) {
        uint4 w[HU];
#pragma unroll
        for (int u = 0; u < HU; u++) w[u] = ldg_stream4(P.w_mod + (size_t)(r + u) * NMOD + col);
#pragma unroll
        for (int u = 0; u < HU; u++) {
          float s = sc[r + u];
          acc[0] += s * bf_lo(w[u].x); acc[1] += s * bf_hi(w[u].x); acc[2] += s * bf_lo(w[u].y); acc[3] += s * bf_hi(w[u].y);
          acc[4] += s * bf_lo(w[u].z); acc[5] += s * bf_hi(w[u].z); acc[6] += s * bf_lo(w[u].w); acc[7] += s * bf_hi(w[u].w);
        }
      }
      if (tid >= 128) {
#pragma unroll
        for (int e = 0; e < 8; e++) red[(tid & 127) * 8 + e] = acc[e];
      }
      const uint32_t tag = ld_relaxed(&g_epoch) % 3 + 1;
      bar_sync(1, 256);
      if (tid < 128) {
        uint32_t o[8];
#pragma unroll
        for (int e = 0; e < 8; e++) o[e] = __float_as_uint(rbf(acc[e] + red[tid * 8 + e])) | tag;
        st_relaxed4(g_mod + col, o[0], o[1], o[2], o[3]);
        st_relaxed4(g_mod + col + 4, o[4], o[5], o[6], o[7]);
        const uint4 wr = ldg_nc4(P.w_r + tid * 8);
        const uint32_t wv[4] = {wr.x, wr.y, wr.z, wr.w};
        float dsum = 0.f;
#pragma unroll
        for (int e = 0; e < 8; e++) {
          const float m = bf_hi(o[e]);
          dsum += (b == NMAIN + 2 ? rbf(1.f + m) : m) * ((e & 1) ? bf_hi(wv[e >> 1]) : bf_lo(wv[e >> 1]));
        }
#pragma unroll
        for (int k = 16; k > 0; k >>= 1) dsum += __shfl_xor_sync(0xffffffffu, dsum, k);
        if (lane == 0) st_relaxed(g_mod + (b - NMAIN) * 4 + warp, tagf(dsum, tag));
      }
    }
    PROF(2, tid == 0, 1);
    return;
  }

  const int rank = b & 1;
  const int rb = ((b >> 4) << 1) | rank, cj = (b >> 1) & 7;
  const bool late = b & 4;
  const uint32_t bfull = base + OFF_BAR, bempty = bfull + NSLOT * 8;
  const uint32_t gfull = bempty + NSLOT * 8, gempty = gfull + 32;
  const uint32_t bar_ofull = gempty + 32;
  const uint32_t bar_ofree = bar_ofull + 32;
  const uint32_t bar_par = bar_ofree + 32;
  const uint32_t bar_mod = bar_par + 8;
  const uint32_t bar_pread = bar_mod + 8;
  const uint32_t bar_xres = bar_pread + 8;
  const uint32_t bar_ring = bar_xres + 8;
  const uint32_t bar_box = bar_ring + 24;
  const uint32_t bar_go = bar_box + 96;
  const uint32_t bar_go2 = bar_go + 16;
  const uint32_t bar_cnt = bar_go + 24;
  const uint32_t xfull = bar_go + 40, xempty = xfull + 32;
  const uint32_t bar_hw = xempty + 32, bar_hx = bar_hw + 8;
  const uint32_t bar_hpub = bar_hx + 24;
  const uint32_t bar_win = bar_hpub + 16;
  const uint32_t bar_rx = bar_win + 8;
  const uint32_t bar_sel = bar_rx + 8;
  const uint32_t bar_gate = bar_sel + 8;
  const uint32_t bar_rel = bar_gate + 8;
  const uint32_t bar_od = bar_rel + 8;
  const uint32_t bar_mod2 = bar_od + 8;
  const uint32_t bar_res = bar_go + 8;
  const uint32_t stage = base + OFF_STAGE, par = base + OFF_PAR;

  if (warp == 8 && elect_one()) {
    for (int s = 0; s < NSLOT; s++) { mbar_init(bfull + s * 8, 1); mbar_init(bempty + s * 8, 16); }
    for (int s = 0; s < 4; s++) { mbar_init(gfull + s * 8, 1); mbar_init(gempty + s * 8, 16); mbar_init(xfull + s * 8, 1); mbar_init(xempty + s * 8, 8); mbar_init(bar_ofree + s * 8, 1); mbar_init(bar_ofull + s * 8, 128); }
    mbar_init(bar_par, 64); mbar_init(bar_mod, 256); mbar_init(bar_pread, 2); mbar_init(bar_xres, 1);
    mbar_init(bar_ring, 8); mbar_init(bar_ring + 8, 8); mbar_init(bar_ring + 16, 8);
    mbar_init(bar_go, 1); mbar_init(bar_go2, 1); mbar_init(bar_cnt, 1); mbar_init(bar_cnt + 8, 1); mbar_init(bar_hpub, 8); mbar_init(bar_hpub + 8, 8); mbar_init(bar_res, 1); mbar_init(bar_win, 1); mbar_init(bar_rx, 1); mbar_init(bar_sel, 64); mbar_init(bar_gate, 8); mbar_init(bar_rel, 8); mbar_init(bar_od, 1); mbar_init(bar_mod2, 64);
    for (int s = 0; s < 12; s++) mbar_init(bar_box + s * 8, 1);
    asm volatile("fence.mbarrier_init.release.cluster;" ::: "memory");
    prefetch_map(&maps.x); prefetch_map(&maps.wq); prefetch_map(&maps.k); prefetch_map(&maps.v);
  }
  if (warp == 9 && elect_one()) {
    mbar_init(bar_hw, 1); mbar_init(bar_hx, 1); mbar_init(bar_hx + 8, 1); mbar_init(bar_hx + 16, 1);
    asm volatile("fence.mbarrier_init.release.cluster;" ::: "memory");
    mbar_expect_tx(bar_hw, 32768);
    mbar_expect_tx(bar_hx + 8, 16384);
    const __nv_bfloat16* xs = P.x + (size_t)(rb * 128 + cj * 16) * DM;
    if (late) {
      mbar_expect_tx(bar_hx, 16384);
      mbar_expect_tx(bar_hx + 16, 16384);
      bulk_load(stage, xs - 24 * DM, 16384, bar_hx);
    }
    bulk_load(base + 2 * GST_BYTES, xs, 16384, bar_hx + 8);
    if (late) {
      bulk_load(base + 3 * GST_BYTES, xs + 8 * DM, 16384, bar_hx + 16);
      prefetch_map(&maps.wm);
    } else {
      tma2d(stage, &maps.wm, (b >> 1) * 32, rank * 512, bar_hw);
      tma2d(stage + 16384, &maps.wm, (b >> 1) * 32, rank * 512 + 256, bar_hw);
    }
  }
  cluster_arrive();

  if (warp >= 8) {
    asm volatile("setmaxnreg.dec.sync.aligned.u32 40;");
    if (warp < 10) bar_arrive(1, 320);
    const uint32_t epoch = ld_relaxed(&g_epoch);
    cluster_wait();
    if (warp == 8) {
      const int kvrow = (cj >> 1) * SK + (SK - WIN);
      int wch = cj * 8 + rank * 2;
#pragma unroll 1
      for (int ps = 0; ps < 3; ps++) {
        const CUtensorMap* mw = ps == 2 ? &maps.wo : &maps.wq;
        const uint32_t xt = ps == 1 ? XT1 : XT2, wt = ps == 0 ? WT0 : (ps == 1 ? WT1 : WT2);
        const int nst = ps == 2 ? 32 : 16;
#pragma unroll 1
        for (int i = 0; i < nst; i++) {
          const uint32_t bf = gfull + (i & 3) * 8;
          const int kt = ps == 2 ? (((cj & 1) * 4 + ((i >> 1) & 3)) * 4 + (i >> 3)) * 2 + (i & 1) : (ps ? i : slice_of(i) + (b & 14)) & 15;
          const uint32_t wd = base + unit_of(wt, i & 3) + rank * UNIT, xd = base + unit_of(xt, i & 3);
          const uint8_t* xs = g_act + (uint32_t)(rb * 80 + (ps - 1) * 16 + kt) * UNIT;
          if (ps == 0 && i == HD) mbar_wait(bar_mod, 0);
          const bool xfirst = ps && i < 2;
          if (ps == 2 && i == 0) mbar_wait(bar_ofree + 24, 0);
          if (i == 0) fence_async();
          mbar_wait(gempty + (i & 3) * 8, ((i >> 2) & 1) ^ 1);
          if (elect_one()) {
            mbar_expect_tx(bf, ps ? GST_BYTES : 2 * UNIT);
            if (xfirst) bulk_load_stream(xd, xs, UNIT, bf);
          }
          if (ps && i < 4) mbar_wait(bempty + i * 8, 1);
          if (elect_one()) tma3d_mc<true>(wd, mw, 0, (i == 31 ? kt ^ (rank * 32) : kt) * 64, i == 31 ? cj * 2 : wch, bf);
          if (ps) {
            if (i == 16 || i == 24) { mbar_wait(bar_cnt + i - 16, 0); fence_async(); }
            if (i == RES0) mbar_wait(bar_res, 0);
            if (i == 2) mbar_wait(bar_ofree + (ps - 1) * 16, 0);
            if (elect_one()) {
              if (i == 31) bulk_load(xd, xs, UNIT, bf); else if (!xfirst) bulk_load_stream(xd, xs, UNIT, bf);
              mbar_arrive_pred(bar_go, i == GOST - 1);
              if (PG0 < 16) mbar_arrive_pred(bar_go2, ps == 1 && i == PG0);
              mbar_arrive_pred(bar_od, i == (ps == 1 ? ODS1 : ODS));
              if (i == RES0) mbar_expect_tx(bar_xres, 32768);
              if (i == RES0 || i == RES1) tma2d(base + OFF_RES + (i == RES1) * UNIT, &maps.x, cj * 128 + (i == RES1) * 64, rb * 128, bar_xres);
            }
          }
        }
        if (ps == 2) break;
        wch = ps ? ((wch >> 3) ^ rank) * 2 : wch + 4;
#pragma unroll 1
        for (int u = 0; u < 16; u++) {
          const bool isk = (u == 0) || ((u & 1) && u < 15);
          const int blk = (isk ? (u + 1) >> 1 : (u == 15 ? 7 : (u >> 1) - 1)) & 3;
          const uint32_t sl = base + unit_of(ps ? AT1 : AT0, u & 3) + rank * UNIT, bf = bfull + (u & 3) * 8;
          if (u < 4) mbar_wait(gempty + ((u + 1) >> 1) * 8, 1);
          mbar_wait(bempty + (u & 3) * 8, ((u >> 2) & 1) ^ 1);
          if (elect_one()) {
            mbar_arrive_pred(bar_go2, ps && u + 16 == PG0);
            mbar_expect_tx(bf, SLOT_BYTES);
            tma3d_mc<false>(sl, isk ? &maps.k : &maps.v, 0, kvrow + blk * 128, rank, bf);
          }
        }
      }
      if (elect_one()) mbar_expect_tx(bar_rx, UNIT);
      mbar_wait(bar_rel, 0);
      if (elect_one()) {
        bulk_load_stream(base + UNIT, g_act + (uint32_t)(rb * 80 + 16 + 63 - (cj & 1) * 32) * UNIT, UNIT, bar_rx);
      }
      if (b < NFFN) {
#pragma unroll 1
        for (int u = 0; u < 12; u++) {
          const uint32_t dst = base + unit_of(u < 4 ? FT_G : (u < 8 ? FT_U : FT_D), u & 3);
          if (elect_one()) mbar_expect_tx(bar_box + u * 8, UNIT);
          if (u == FB0 || u == FB1 || u == FB2) mbar_wait(bar_ring + (u == FB2 ? 16 : u == FB1 ? 8 : 0), 0);
          const int fp = u < FPB ? FPACE0 : FPACE;
          if (u >= fp) mbar_wait(bar_box + (u - fp) * 8, 0);
          if (elect_one()) {
            if (u < 8) tma2d(dst, u < 4 ? &maps.wg : &maps.wu, b * 32, (u & 3) * 256, bar_box + u * 8);
            else tma3d(dst, &maps.wd, 0, b * 32, (u - 8) * 4, bar_box + u * 8);
          }
        }
      }
    } else if (warp == 9) {
      const uint32_t target = 8 * (epoch + 1);
      uint32_t hmask = 0;
#pragma unroll 1
      for (int i = 0; i < 16; i++) {
        if (i == HDX) mbar_wait(bar_mod, 0);
        const int kt = (2 * cj + slice_of(i)) & 15;
        const uint32_t need = i == 15 ? 0xffffu : 1u << kt;
        if (i >= NRS && (hmask & need) != need) {
          uint32_t n = 0;
          do { hmask = __ballot_sync(0xffffffffu, ld_acquire(&g_cnt_h[rb * 32 + (lane & 15)]) == epoch + 1); watchdog(n); } while ((hmask & need) != need);
          PROF(1, lane == 0 && i == NRS, 26);
          fence_async();
        }
        mbar_wait(xempty + (i & 3) * 8, ((i >> 2) & 1) ^ 1);
        if (elect_one()) {
          mbar_expect_tx(xfull + (i & 3) * 8, UNIT);
          if (i < NRS) tma2d(base + (i & 3) * GST_BYTES, &maps.x, kt * 64, rb * 128, xfull + (i & 3) * 8);
          else bulk_load_stream(base + (i & 3) * GST_BYTES, g_act + (uint32_t)(rb * 80 + kt) * UNIT, UNIT, xfull + (i & 3) * 8);
        }
      }
      prefetch_map(&maps.wo);
#pragma unroll 1
      for (int t = 0; t < 4; t++) {
        if (t & 1) mbar_wait(bar_od, t >> 1);
#pragma unroll 1
        for (int p = 0; p < 32768 / OPS; p++) {
          const uint32_t w = p / (16384 / OPS), c = (p / (8192 / OPS)) & 1, off = w * 8192 + (p % (8192 / OPS)) * OPS;
          mbar_wait(bar_ofull + (t & 1) * 16 + w * 8, t >> 1);
          if (elect_one()) {
            bulk_store(g_act + (uint32_t)(rb * 80 + 16 + (cj * 4 + t) * 2 + c) * UNIT + off, base + unit_of(QT, 2 * t + c) + off, OPS);
            asm volatile("cp.async.bulk.commit_group;" ::: "memory");
            asm volatile("cp.async.bulk.wait_group.read %0;" ::"n"(OFL) : "memory");
          }
        }
        if (elect_one()) {
          asm volatile("cp.async.bulk.wait_group.read 0;" ::: "memory");
          mbar_arrive(t < 3 ? bar_ofree + t * 8 : bar_res);
          asm volatile("cp.async.bulk.wait_group 0;" ::: "memory");
          fence_async();
          red_release(&g_cnt_o[((rb * 4 + t) * 2 + (cj >> 2)) * 32], 2);
        }
        if (t) {
          wait_counter(&g_cnt_o[(rb * 8 + 2 * t + (cj & 1)) * 32], target);
          if (t & 1) wait_counter(&g_cnt_o[(rb * 8 + (t == 1 ? cj & 1 : 7 - (cj & 1))) * 32], target);
          if (elect_one()) mbar_arrive(t == 1 ? bar_ofree + 24 : bar_cnt + t * 8 - 16);
        }
      }
      PROF(2, lane == 0, 27);
      const uint32_t tag = epoch % 3 + 1;
      const uint32_t* inbox = g_cand + (lane & 15);
      mbar_wait(bar_ring + 16, 0);
      uint32_t c0 = ld_relaxed(inbox), n = 0;
#define CAND_STEP(cv)                                                                                        \
      {                                                                                                      \
        const bool valid = (cv & 3u) == tag, all = __all_sync(0xffffffffu, valid);                           \
        const uint32_t best = __reduce_max_sync(0xffffffffu, valid ? cv : 0u);                               \
        const uint32_t blk = __ffs(__ballot_sync(0xffffffffu, cv == best)) - 1;                              \
        if (best) sts2(par + PAR_CONST + 56, best, (blk << 7 | (~best >> 2 & 127)) | (all ? 0x1800 : 0x800)); \
        if (all) break;                                                                                      \
        cv = ld_relaxed(inbox);                                                                              \
      }
      while (true) { CAND_STEP(c0) watchdog(n); }
    } else {
      const int t2 = tid - 320;
      if (late && warp == 10) {
        bar_sync(5, 288);
        if (HWB) mbar_wait(bar_hx + HWB * 8, 0);
        if (elect_one()) {
          tma2d(stage, &maps.wm, (b >> 1) * 32, rank * 512, bar_hw);
          tma2d(stage + 16384, &maps.wm, (b >> 1) * 32, rank * 512 + 256, bar_hw);
        }
      }
      {
        const uint32_t tag = epoch % 3 + 1;
        mbar_wait(bar_hw, 0);
        {
          const uint32_t t7 = (warp & 1) * 64 + (lane >> 4) * 32 + 16 + (lane & 15);
          const uint32_t* pm = g_modp + ((cj * 128 + t7 * 4) & (DM - 1));
          uint4 m0, m1, m2, m3;
          uint32_t n = 0;
          do {
            m0 = ld_relaxed4(pm); m1 = ld_relaxed4(pm + 2 * DM); m2 = ld_relaxed4(pm + DM); m3 = ld_relaxed4(pm + 3 * DM);
            watchdog(n);
          } while (!__all_sync(0xffffffffu, tag_ok(m0, tag) && tag_ok(m1, tag) && tag_ok(m2, tag) && tag_ok(m3, tag)));
          write_table(par, false, t7, m0, m1);
          write_table(par, true, t7, m2, m3);
          mbar_arrive(bar_mod2);
        }
      }
      mbar_wait(bar_hpub + (warp & 1) * 8, 0);
      PROF(1, t2 == 0, 24);
#pragma unroll 1
      for (int c = 0; c < 8; c++) {
        const uint32_t off = (warp & 1) * UNIT + c * 2048 + lane * 16;
        uint8_t* dst = g_act + (uint32_t)(rb * 80 + cj * 2) * UNIT + off;
        const uint4 v0 = lds4(stage + off), v1 = lds4(stage + off + 512), v2 = lds4(stage + off + 1024), v3 = lds4(stage + off + 1536);
        stg4(dst, v0); stg4(dst + 512, v1); stg4(dst + 1024, v2); stg4(dst + 1536, v3);
      }
      __syncwarp();
      PROF(1, t2 == 0, 15);
      if (lane == 0) {
        mbar_arrive(bar_pread);
        red_release(&g_cnt_h[rb * 32 + cj * 2 + (warp & 1)], 1);
        PROF(1, t2 == 0, 25);
        prefetch_map(&maps.wg); prefetch_map(&maps.wu); prefetch_map(&maps.wd); prefetch_map(&maps.out);
      }
      __syncwarp();
      if (b < NFFN) {
        mbar_wait(bar_go2, 0);
        const __nv_bfloat16* pg = ((b & 1) ? P.w_up : P.w_gate) + (b >> 1) * 64 + (size_t)t2 * FF;
        const __nv_bfloat16* pd = P.w_down + (size_t)b * 32768 + t2 * 64;
        PROF(2, t2 == 0, 13);
#pragma unroll 1
        for (int i = 0; i < WN; i += WB) {
          uint32_t v[WB];
#pragma unroll
          for (int u = 0; u < WB; u++) {
            const int k = i + u;
            asm volatile("ld.global.cg.L2::128B.u32 %0, [%1];" : "=r"(v[u]) : "l"(k < 16 ? pg + (size_t)k * 64 * FF : pd + (k - 16) * 4096));
          }
#pragma unroll
          for (int u = 1; u < WB; u++) v[0] ^= v[u];
          sts1(par + PAR_SINK + t2 * 4, v[0]);
        }
        PROF(2, t2 == 0, 14);
      }
      const uint32_t tag = epoch % 3 + 1;
      mbar_wait(bar_go, 0);
      bar_sync(4, 64);
      if (warp == 10) {
        const uint32_t* src = g_mod + 2 * DM + cj * 128 + lane * 4;
        const uint2 wr = *reinterpret_cast<const uint2*>(P.w_r + cj * 128 + lane * 4);
        uint4 vga, vsb, vcb, vgb;
        uint32_t n = 0;
        do {
          vga = ld_relaxed4(src); vsb = ld_relaxed4(src + DM); vcb = ld_relaxed4(src + 2 * DM); vgb = ld_relaxed4(src + 3 * DM);
          watchdog(n);
        } while (!__all_sync(0xffffffffu, tag_ok(vga, tag) && tag_ok(vsb, tag) && tag_ok(vcb, tag) && tag_ok(vgb, tag)));
        const float c0 = rbf(1.f + bf_hi(vcb.x)), c1 = rbf(1.f + bf_hi(vcb.y)), c2 = rbf(1.f + bf_hi(vcb.z)), c3 = rbf(1.f + bf_hi(vcb.w));
        const float a0 = c0 * bf_lo(wr.x), a1 = c1 * bf_hi(wr.x), a2 = c2 * bf_lo(wr.y), a3 = c3 * bf_hi(wr.y);
        const uint32_t h0 = pack_bf(a0, a1), h1 = pack_bf(a2, a3);
        const uint32_t t1 = par + PAR_T1 + (lane >> 2) * 64 + (lane & 1) * 32 + (lane & 2) * 2;
        sts1(t1, h0); sts1(t1 + 8, pack_bf(a0 - bf_lo(h0), a1 - bf_hi(h0)));
        sts1(t1 + 16, h1); sts1(t1 + 24, pack_bf(a2 - bf_lo(h1), a3 - bf_hi(h1)));
        const uint32_t tg = par + PAR_SINK + (lane >> 3) * 64 + (lane & 1) * 32 + (lane & 6) * 2;
        sts1(tg, __byte_perm(vga.x, vga.y, 0x7632)); sts1(tg + 16, __byte_perm(vga.z, vga.w, 0x7632));
        sts4(par + PAR_T2 + lane * 32, make_uint4(pack_bf(c0, c1), __byte_perm(vsb.x, vsb.y, 0x7632), __byte_perm(vgb.x, vgb.y, 0x7632), __byte_perm(vga.x, vga.y, 0x7632)));
        sts4(par + PAR_T2 + lane * 32 + 16, make_uint4(pack_bf(c2, c3), __byte_perm(vsb.z, vsb.w, 0x7632), __byte_perm(vgb.z, vgb.w, 0x7632), __byte_perm(vga.z, vga.w, 0x7632)));
      } else {
        const uint4 g = poll4((lane & 2) ? g_mod + 8 - (lane & 1) * 4 : g_mod + 5 * DM + b * 8 + (lane & 1) * 4, tag);
        sts1(par + PAR_CONST + 60, 0);
        if (lane < 2) sts4(par + PAR_CONST + 16 + lane * 16, g);
        else if (lane < 4) sts2(par + PAR_CONST + (lane - 2) * 8, __float_as_uint(untag_sum(g.x, g.y) + untag_sum(g.z, g.w)), epoch);
      }
      __syncwarp();
#pragma unroll 4
      for (int q = 0; q < 32; q++) st_b128(g_xch + ((size_t)b * 8 * 256 + q * 64 + t2) * 4, (epoch & 1) << 16, 0, 0, 0);
      for (int q = 0; q < 2; q++) st_relaxed4(g_stats + ((size_t)cj * SEQ + rb * 128 + q * 64 + t2) * 4, 0, 0, 0, 0);
      if (b < NFFN)
        for (int q = 0; q < 4; q++) st_relaxed4(g_ypart + ((size_t)(q * 32 + (t2 >> 1)) * NFFN + b) * 8 + (t2 & 1) * 4, 0, 0, 0, 0);
      st_relaxed4(g_row + rb * 2 * DM + (t2 >> 5) * DM + cj * 128 + (t2 & 31) * 4, 0, 0, 0, 0);
      __threadfence();
      mbar_arrive(bar_par);
      mbar_wait(bar_gate, 0);
      uint32_t have = 0, n = 0;
      while (true) {
        const uint32_t st = lds1(par + PAR_CONST + 60) >> 7;
        if ((st & 31) != have) {
          const uint32_t* hsrc = g_row + (st & 15) * 2 * DM + t2 * 4;
          uint4 hv[4];
          bool ok = true;
#pragma unroll
          for (int i = 0; i < 4; i++) hv[i] = ld_pairs(hsrc + i * 256);
#pragma unroll
          for (int i = 0; i < 4; i++) {
            sts2(base + ((FT_G >> i * 4) & 15) * UNIT + (warp & 1) * 8192 + 256 + lane * 8, hv[i].x, hv[i].z);
            ok = ok && hv[i].y == tag && hv[i].w == tag;
          }
          have = __all_sync(0xffffffffu, ok) ? st & 31 : 0;
        }
        if ((st ^ have) == 32) break;
        watchdog(n);
      }
      mbar_arrive(bar_sel);
    }
    __syncwarp();
    cluster_arrive();
    {
      const uint32_t tag = epoch % 3 + 1, t3 = tid - 256;
      mbar_wait(bar_win, 0);
      uint2 win = lds2(par + PAR_CONST + 56);
      win.y &= 0x7ff;
      const uint32_t* fsrc = g_row + (win.y >> 7) * 2 * DM + (b >> 1) * 16 + (t3 & 3) * 4 + (b & 1) * 2;
      const uint32_t* ysrc = g_ypart + (size_t)b * NFFN * 8 + min(t3, NFFN - 1) * 4;
      uint2 fh = ld_pair(fsrc), fx = ld_pair(fsrc + DM);
      if (PSL) __nanosleep(PSL);
      uint4 ya = ld_relaxed4(ysrc), yb = ld_relaxed4(ysrc + NFFN * 4);
      const float rwin = __uint_as_float(((int)win.x < 0 ? win.x & 0x7fffffffu : ~win.x) & ~0x1ffu);
      const float rs = rbf(rcp(1.f + __expf(-rbf(rwin))));
      uint32_t n = 0;
      while (__any_sync(0xffffffffu, fh.y != tag || fx.y != tag)) { fh = ld_pair(fsrc); fx = ld_pair(fsrc + DM); watchdog(n); }
      while (!__all_sync(0xffffffffu, tag_ok(ya, tag) && tag_ok(yb, tag))) {
        if (!tag_ok(ya, tag)) ya = ld_relaxed4(ysrc);
        if (!tag_ok(yb, tag)) yb = ld_relaxed4(ysrc + NFFN * 4);
        watchdog(n);
      }
      __syncwarp();
      PROF(8, t3 == 0, 5);
      float y0 = untag_sum(ya.x, yb.x), y1 = untag_sum(ya.y, yb.y), y2 = untag_sum(ya.z, yb.z), y3 = untag_sum(ya.w, yb.w);
      const bool u1 = lane & 2, u2 = lane & 4;
      y0 = (u1 ? y2 : y0) + __shfl_xor_sync(0xffffffffu, u1 ? y0 : y2, 2);
      y1 = (u1 ? y3 : y1) + __shfl_xor_sync(0xffffffffu, u1 ? y1 : y3, 2);
      y0 = (u2 ? y1 : y0) + __shfl_xor_sync(0xffffffffu, u2 ? y0 : y1, 4);
      y0 += __shfl_xor_sync(0xffffffffu, y0, 8);
      if (!(lane & 8)) sts1(par + PAR_RED + 64 + (t3 >> 4) * 32 + ((lane & 1) * 4 + (lane & 2) + ((lane >> 2) & 1)) * 4, __float_as_uint(y0));
      bar_sync(4, 128);
      if (t3 < 4) {
        y0 = 0.f; y1 = 0.f;
#pragma unroll
        for (int w4 = 0; w4 < 7; w4++) {
          const uint2 v = lds2(par + PAR_RED + 64 + w4 * 32 + t3 * 8);
          y0 += __uint_as_float(v.x); y1 += __uint_as_float(v.y);
        }
        const uint2 gv = lds2(par + PAR_CONST + 16 + t3 * 8);
        const uint32_t upd = hmul2(pack_bf(y0, y1), pack_bf(rs, rs));
        *reinterpret_cast<uint32_t*>(P.out + (size_t)win.y * DM + b * 8 + t3 * 2) =
            hadd2(fx.x, hmul2(__byte_perm(gv.x, gv.y, 0x7632), hadd2(fh.x, upd)));
        if (b == 0 && t3 == 0) st_relaxed(&g_epoch, epoch + 1);
      }
      PROF(31, t3 == 0, 36);
    }
    cluster_wait();
  } else {
    const int wg = warp >> 2;

    uint32_t tag, sc[8];
    uint32_t* const pmod = g_modp + rank * 2 * DM + (b >> 1) * 32 + lane;
    {
      uint32_t* const pln = g_ln1 + (rb * 128 + cj * 16 + warp) * 4;
#pragma unroll
      for (int k = 0; k < 8; k++) sc[k] = ldg_nc1(P.c + rank * 512 + warp * 64 + k * 8 + (lane & 3) * 2);
      const uint32_t epoch = ld_relaxed(&g_epoch);
      if (warp == 0) st_relaxed(pmod, 0);
      if (lane == 0) {
        st_b128(pln, 0, 0, 0, 0);
        if (late) { st_b128(pln - 96, 0, 0, 0, 0); st_b128(pln + 32, 0, 0, 0, 0); }
      }
      asm volatile("setmaxnreg.inc.sync.aligned.u32 232;");
      bar_sync(1, 320);
#pragma unroll
      for (int k = 0; k < 8; k++) sc[k] = pack_bf(silu_f(bf_lo(sc[k])), silu_f(bf_hi(sc[k])));
      keep(sc);
      tag = epoch % 3 + 1;
#pragma unroll 1
      for (int part = !late; part < (late ? 3 : 2); part++) {
        {
          const uint32_t xa = (part ? base + (1 + part) * GST_BYTES : stage) + warp * 2048 + lane * 16;
          mbar_wait(bar_hx + part * 8, 0);
          float s0 = 0.f, s1 = 0.f, q0 = 0.f, q1 = 0.f;
#pragma unroll
          for (int q = 0; q < 4; q++) {
            const uint4 xv = lds4(xa + q * 512);
            const uint32_t u[4] = {xv.x, xv.y, xv.z, xv.w};
#pragma unroll
            for (int e = 0; e < 4; e++) { const float lo = bf_lo(u[e]), hi = bf_hi(u[e]); s0 += lo; s1 += hi; q0 += lo * lo; q1 += hi * hi; }
          }
          s0 += s1; q0 += q1;
          if (part == 0) bar_arrive(5, 288);
#pragma unroll
          for (int o = 16; o > 0; o >>= 1) { s0 += __shfl_xor_sync(0xffffffffu, s0, o); q0 += __shfl_xor_sync(0xffffffffu, q0, o); }
          const float mean = s0 * (1.f / DM);
          float mb, sd;
          ln_scalars(mean, fmaxf(q0 * (1.f / DM) - mean * mean, 0.f), mb, sd);
          uint32_t ih, il;
          split_inv(sd, ih, il);
          if (lane == 0) st_b128(pln + (part ? part * 32 - 32 : -96), pack_bf(mb, mb), ih, il, tag);
        }
      }
      PROF(1, tid == 0, 4);
    }
    auto gemv = [&]() {
      {
        {
          const uint32_t fr = (lane & 7) + (lane >> 4) * 8, tq = lane & 3;
          const uint32_t wa = stage + warp * 4096 + fr * 64 + ((((lane >> 3) & 1) ^ ((fr >> 1) & 3)) << 4);
          float d0[4] = {0.f, 0.f, 0.f, 0.f}, d1[4] = {0.f, 0.f, 0.f, 0.f};
          mbar_wait(bar_hw, 0);
#pragma unroll
          for (int ks = 0; ks < 4; ks++) {
            uint32_t w[8];
            ldmatrix4t(wa + ks * 1024, w[0], w[1], w[2], w[3]);
            ldmatrix4t((wa ^ 32) + ks * 1024, w[4], w[5], w[6], w[7]);
            mma16816(d0, w[0], w[1], w[2], w[3], sc[2 * ks], sc[2 * ks + 1]);
            mma16816(d1, w[4], w[5], w[6], w[7], sc[2 * ks], sc[2 * ks + 1]);
          }
          sts1(base + 2 * GST_BYTES + warp * 2048 + (tq * 8 + (lane >> 2)) * 4, __float_as_uint((tq & 2) ? ((tq & 1) ? d1[2] : d1[0]) : ((tq & 1) ? d0[2] : d0[0])));
          bar_sync(1, 256);
          if (warp == 0) {
            float s = 0.f;
#pragma unroll
            for (int w8 = 0; w8 < 8; w8++) s += __uint_as_float(lds1(base + 2 * GST_BYTES + w8 * 2048 + lane * 4));
            st_relaxed(pmod, (__float_as_uint(s) & ~3u) | tag);
          }
          PROF(1, tid == 0, 3);
        }
      }
    };
    if (!late || !GLATE) gemv();
    cluster_wait();
    if (wg == 1) bar_arrive(2, 256);

    float f0 = 0.f, f1 = 0.f;
    const uint32_t rempty = lane < 2 ? mapa(bempty, lane & 1) : 0;
    constexpr uint32_t GE = NSLOT * 8 + 32;
    float o[64], s[64];
#pragma unroll 1
    for (int ps = 0; ps < 3; ps++) {
      {
        const uint32_t xt = ps == 1 ? XT1 : XT2, wt = ps == 1 ? WT1 : WT2;
        const int nst = ps == 2 ? 28 : 14;
        if (ps == 0) {
          float ga[64], gb[64];
#pragma unroll
          for (int i = 0; i < 64; i++) { ga[i] = 0.f; gb[i] = 0.f; }
          uint32_t a[2][16];
          const uint32_t l = fresh_lane();
          uint32_t fa[4];
#pragma unroll
          for (int kk = 0; kk < 4; kk++) fa[kk] = (base + wg * 8192 + frag_offset(warp)) ^ (kk * 32);
          const uint32_t mt = par + (l & 3) * 16;
          auto fetch = [&](int i, uint32_t (&f)[16], uint32_t z) {
            mbar_wait(xfull + (i & 3) * 8, i >> 2);
#pragma unroll
            for (int kk = 0; kk < 4; kk++) ldmatrix4(fa[kk] + (i & 3) * GST_BYTES + z, f[4 * kk], f[4 * kk + 1], f[4 * kk + 2], f[4 * kk + 3]);
          };
          const bool oddw = warp & 2;
          uint4 r0, r1;
          {
            const uint32_t t7 = (warp & 1) * 64 + (l >> 4) * 32 + (l & 15);
            const uint32_t* pm = g_modp + wg * DM + ((cj * 128 + t7 * 4) & (DM - 1));
            const uint32_t* pr = g_ln1 + (rb * 128 + warp * 16 + (l >> 2)) * 4;
            uint4 m0 = make_uint4(tag, tag, tag, tag), m1 = m0;
            if (!oddw) { m0 = ld_relaxed4(pm); m1 = ld_relaxed4(pm + 2 * DM); }
            r0 = ld_b128(pr); r1 = ld_b128(pr + 32);
            fetch(0, a[0], 0); fetch(1, a[1], 0);
            uint32_t n = 0;
            bool written = false;
#pragma unroll 1
            while (true) {
              uint32_t miss;
              asm volatile("{ .reg .pred p0, p1, p2, p3; .reg .b32 t, u;\n"
                           "lop3.b32 t, %1, %2, %19, 0x7e; lop3.b32 u, %3, %4, %19, 0x7e; or.b32 t, t, u; and.b32 t, t, 3; setp.ne.u32 p0, t, 0;\n"
                           "lop3.b32 t, %5, %6, %19, 0x7e; lop3.b32 u, %7, %8, %19, 0x7e; or.b32 t, t, u; and.b32 t, t, 3; setp.ne.u32 p1, t, 0;\n"
                           "setp.ne.u32 p2, %12, %19; setp.ne.u32 p3, %16, %19;\n"
                           "@p0 ld.relaxed.gpu.global.v4.u32 {%1, %2, %3, %4}, [%17];\n"
                           "@p1 ld.relaxed.gpu.global.v4.u32 {%5, %6, %7, %8}, [%17 + 8192];\n"
                           "@p2 ld.relaxed.gpu.global.v4.u32 {%9, %10, %11, %12}, [%18];\n"
                           "@p3 ld.relaxed.gpu.global.v4.u32 {%13, %14, %15, %16}, [%18 + 128];\n"
                           "or.pred p0, p0, p1; or.pred p2, p2, p3; vote.sync.any.pred p0, p0, 0xffffffff; vote.sync.any.pred p2, p2, 0xffffffff;\n"
                           "selp.u32 t, 1, 0, p0; selp.u32 u, 2, 0, p2; or.b32 %0, t, u; }"
                           : "=r"(miss), "+r"(m0.x), "+r"(m0.y), "+r"(m0.z), "+r"(m0.w), "+r"(m1.x), "+r"(m1.y), "+r"(m1.z), "+r"(m1.w),
                             "+r"(r0.x), "+r"(r0.y), "+r"(r0.z), "+r"(r0.w), "+r"(r1.x), "+r"(r1.y), "+r"(r1.z), "+r"(r1.w)
                           : "l"(pm), "l"(pr), "r"(tag) : "memory");
              if (!(miss & 1) && !written) {
                written = true;
                if (!oddw) write_table(par, wg, t7, m0, m1);
                mbar_arrive(bar_mod);
              }
              if (!miss) break;
              watchdog(n);
            }
          }
          const uint32_t zero = r0.w ^ tag;
          auto normalize = [&](uint32_t (&f)[16]) {
#pragma unroll
            for (int k = 0; k < 16; k += 2) { f[k] = ln_norm(f[k], r0.x, r0.y, r0.z); f[k + 1] = ln_norm(f[k + 1], r1.x, r1.y, r1.z); }
          };
          auto modulate = [&](int i, uint32_t (&f)[16]) {
#pragma unroll
            for (int kk = 0; kk < 4; kk++) {
              const uint4 m = lds4(mt + slice_of(i) * 256 + kk * 64);
              f[4 * kk] = MODUL(f[4 * kk], m.x, m.z); f[4 * kk + 1] = MODUL(f[4 * kk + 1], m.x, m.z);
              f[4 * kk + 2] = MODUL(f[4 * kk + 2], m.y, m.w); f[4 * kk + 3] = MODUL(f[4 * kk + 3], m.y, m.w);
            }
            keep(f);
            mbar_arrive_pred(xempty + (i & 3) * 8, l == 0);
          };
          auto publish = [&](int u, uint32_t (&f)[16]) {
#pragma unroll
            for (int kk = 0; kk < 4; kk++) stmatrix4(fa[kk] + OFF_STAGE + u * UNIT, f[4 * kk], f[4 * kk + 1], f[4 * kk + 2], f[4 * kk + 3]);
            __syncwarp();
            mbar_arrive_pred(bar_hpub + u * 8, l == 0);
          };
          auto multiply = [&](int i, uint32_t (&f)[16]) {
            mbar_wait(gfull + (i & 3) * 8, i >> 2);
            const uint64_t db = make_desc(base + (i & 3) * GST_BYTES + UNIT, 8192, 1024);
            wg_fence();
#pragma unroll
            for (int kk = 0; kk < 4; kk++) mma256_rs(ga, gb, f[4 * kk], f[4 * kk + 1], f[4 * kk + 2], f[4 * kk + 3], db + kk * 128);
            wg_commit();
          };
          auto next = [&](int i, uint32_t (&f)[16]) {
            wg_wait<1>();
            mbar_arrive_cl(rempty, GE + ((i + 2) & 3) * 8);
            uint32_t z = zero;
#pragma unroll
            for (int k = 0; k < 16; k += 2) asm volatile("lop3.b32 %0, %1, %2, %0, 0xA8;" : "+r"(z) : "r"(f[k]), "r"(f[k + 1]));
            fetch(i, f, z);
            normalize(f);
            if (i == 2) { keep(f); mbar_wait(bar_mod2, 0); }
            modulate(i, f); multiply(i, f);
          };
          normalize(a[0]); normalize(a[1]);
          keep(a[0]); keep(a[1]);
          mbar_wait(bar_mod, 0);
          PROF(1, tid == 0, 2);
          modulate(0, a[0]); multiply(0, a[0]); publish(0, a[0]);
          modulate(1, a[1]); multiply(1, a[1]);
#pragma unroll 1
          for (int i = 2; i < NRS; i += 2) {
            next(i, a[0]);
            if (i == 2) publish(1, a[0]);
            next(i + 1, a[1]);
          }
          wg_wait<1>();
          mbar_arrive_cl(rempty, GE + ((NRS + 2) & 3) * 8);
#pragma unroll 1
          for (int i = NRS; i < 14; i++) {
            mbar_wait(xfull + (i & 3) * 8, (i >> 2) & 1);
            mbar_wait(gfull + (i & 3) * 8, (i >> 2) & 1);
            const uint32_t xa = base + (i & 3) * GST_BYTES;
            const uint64_t da = make_desc(xa + wg * 8192, 16, 1024), db = make_desc(xa + UNIT, 8192, 1024);
            if (i == 13) bar_sync(2 + wg, 256);
            wg_fence();
#pragma unroll
            for (int kk = 0; kk < 4; kk++) mma256_ss(ga, gb, da + kk * 2, db + kk * 128, 1);
            wg_commit();
            if (i == 13) bar_arrive(3 - wg, 256);
            wg_wait<1>();
            uint32_t z = zero;
#pragma unroll
            for (int k = 0; k < 16; k += 2) asm volatile("lop3.b32 %0, %1, %2, %0, 0xA8;" : "+r"(z) : "r"(a[1][k]), "r"(a[1][k + 1]));
            mbar_arrive_cl(rempty, GE + ((i + 3) & 3) * 8 + z);
            mbar_arrive_pred(xempty + ((i + 3) & 3) * 8, l == 0 && i != NRS);
          }
          mbar_wait(xfull + 16, 1);
          wg_wait<0>();
          keep(ga); keep(gb);
#pragma unroll
          for (int i = 0; i < 64; i++) {
            asm volatile("mov.b32 %0, %1;" : "=f"(s[i]) : "f"(ga[i]));
            asm volatile("mov.b32 %0, %1;" : "=f"(o[i]) : "f"(gb[i]));
          }
        } else {
          float ga[64], gb[64];
#pragma unroll
          for (int i = 0; i < 64; i++) {
            asm volatile("mov.b32 %0, %1;" : "=f"(ga[i]) : "f"(s[i]));
            asm volatile("mov.b32 %0, %1;" : "=f"(gb[i]) : "f"(o[i]));
          }
#pragma unroll 1
          for (int i = 0; i < nst; i++) {
            mbar_wait(gfull + (i & 3) * 8, (i >> 2) & 1);
            const uint64_t da = make_desc(base + unit_of(xt, i & 3) + wg * 8192, 16, 1024), db = make_desc(base + unit_of(wt, i & 3), 8192, 1024);
            if (i == nst - 1) bar_sync(2 + wg, 256);
            wg_fence();
#pragma unroll
            for (int kk = 0; kk < 4; kk++) mma256_ss(ga, gb, da + kk * 2, db + kk * 128, kk ? 1 : i);
            wg_commit();
            if (i == nst - 1) bar_arrive(3 - wg, 256);
            wg_wait<1>();
            mbar_arrive_cl(rempty, GE + ((i + 3) & 3) * 8, i != 0);
            PROF(4, tid == 0 && (i & 3) == 0, 40 + (ps - 1) * 4 + i / 4);
          }
          wg_wait<0>();
          keep(ga); keep(gb);
#pragma unroll
          for (int i = 0; i < 64; i++) {
            asm volatile("mov.b32 %0, %1;" : "=f"(s[i]) : "f"(ga[i]));
            asm volatile("mov.b32 %0, %1;" : "=f"(o[i]) : "f"(gb[i]));
          }
        }
        mbar_arrive_cl(rempty, GE + (ps == 2 ? 24 : 8));
        if (ps == 2) break;
      }
      const uint32_t qw = base + wg * 8192, qt = QT >> (16 * ps), at = ps ? AT1 : AT0;
      {
        const uint32_t wt = ps ? WT1 : WT0;
        const uint64_t da0 = make_desc(qw + unit_of(qt, 2), 16, 1024), da1 = make_desc(qw + unit_of(qt, 3), 16, 1024);
        const uint64_t db0 = make_desc(base + unit_of(wt, 2), 8192, 1024), db1 = make_desc(base + unit_of(wt, 3), 8192, 1024);
        mbar_wait(gfull + 16, 1);
        bar_sync(2 + wg, 256);
        wg_fence();
#pragma unroll
        for (int kk = 0; kk < 4; kk++) mma_ss<1>(s, da0 + kk * 2, db0 + kk * 128, 1);
        wg_commit();
        mbar_wait(xfull + 24, 1);
        mbar_wait(gfull + 24, 1);
        wg_fence();
#pragma unroll
        for (int kk = 0; kk < 4; kk++) mma_ss<1>(s, da1 + kk * 2, db1 + kk * 128, 1);
        wg_commit();
        bar_arrive(3 - wg, 256);
        mbar_wait(ps == 0 ? bar_pread : bar_ofree + 8, 0);
        wg_wait<0>();
        keep(s);
        PROF(2, tid == 0, 8 + ps * 8);
        uint32_t q[32];
        pack_p(s, q);
#pragma unroll
        for (int i = 0; i < 4; i++) stmatrix4((qw + unit_of(qt, 0) + frag_offset(warp)) ^ (i << 5), q[4 * i], q[4 * i + 1], q[4 * i + 2], q[4 * i + 3]);
        keep(q);
        bar_sync(2 + wg, 256);
        wg_fence();
#pragma unroll
        for (int kk = 0; kk < 8; kk++) mma_ss<1>(o, (kk < 4 ? da0 : da1) + (kk & 3) * 2, (kk < 4 ? db0 : db1) + UNIT / 16 + (kk & 3) * 128, 1);
        wg_commit();
        mbar_wait(bfull, 0);
        wg_fence();
        const uint64_t dk = make_desc(base + unit_of(at, 0), 16, 1024);
#pragma unroll
        for (int kk = 0; kk < 8; kk++) mma_rs<0>(s, q[4 * kk], q[4 * kk + 1], q[4 * kk + 2], q[4 * kk + 3], dk + (kk >> 2) * 1024 + (kk & 3) * 2, kk != 0);
        wg_commit();
        bar_arrive(3 - wg, 256);
#pragma unroll
        for (int i = 4; i < 8; i++) stmatrix4((qw + unit_of(qt, 1) + frag_offset(warp)) ^ ((i & 3) << 5), q[4 * i], q[4 * i + 1], q[4 * i + 2], q[4 * i + 3]);
        wg_wait<1>();
        keep(o);
        mbar_arrive_cl(rempty, GE + 16);
        mbar_arrive_cl(rempty, GE + 24);
        store_chunk<0>(o, qw + unit_of(qt, 2) + frag_offset(warp));
        store_chunk<1>(o, qw + unit_of(qt, 3) + frag_offset(warp));
        wg_wait<0>();
        keep(s);
        mbar_arrive_cl(rempty, 0);
      }
      PROF(4, tid == 0 && ps == 1, 61);
      float l0 = 0.f, l1 = 0.f;
      auto step = [&](auto odd_c, const int j, uint32_t (&pw)[32], uint32_t (&pr)[32]) {
        constexpr bool ODD = decltype(odd_c)::value;
        const bool first = !ODD && (j & 2) == 0, last = ODD && j == 7;
        const uint32_t ph = (j >> 1) & 1;
        float i0, i1, a0, a1;
        const bool so = !ODD && j == 4;
        if (so) { i0 = inv_quad_sum(l0); i1 = inv_quad_sum(l1); l0 = 0.f; l1 = 0.f; }
        bool redo = !ODD && (j | ps) == 0;
        while (true) {
          if (redo) {
            float m0 = fmaxf(s[0], s[1]), m1 = fmaxf(s[2], s[3]);
#pragma unroll
            for (int i = 1; i < 16; i++) { m0 = fmaxf(m0, fmaxf(s[4 * i], s[4 * i + 1])); m1 = fmaxf(m1, fmaxf(s[4 * i + 2], s[4 * i + 3])); }
            m0 = fmaxf(m0, __shfl_xor_sync(0xffffffffu, m0, 1)); m1 = fmaxf(m1, __shfl_xor_sync(0xffffffffu, m1, 1));
            m0 = fmaxf(m0, __shfl_xor_sync(0xffffffffu, m0, 2)); m1 = fmaxf(m1, __shfl_xor_sync(0xffffffffu, m1, 2));
            m0 *= SCL2; m1 *= SCL2;
            if (!first) {
              m0 = fmaxf(m0, f0); m1 = fmaxf(m1, f1);
              const float c0 = ex2(f0 - m0), c1 = ex2(f1 - m1);
              l0 *= c0; l1 *= c1;
              wg_wait<0>();
              keep(o);
#pragma unroll
              for (int i = 0; i < 16; i++) { o[4 * i] *= c0; o[4 * i + 1] *= c0; o[4 * i + 2] *= c1; o[4 * i + 3] *= c1; }
            }
            f0 = m0; f1 = m1;
          }
          float b0 = 0.f, b1 = 0.f;
          a0 = 0.f; a1 = 0.f;
#pragma unroll
          for (int i = 0; i < 16; i++) {
            const float e0 = ex2(fmaf(s[4 * i], SCL2, -f0)), e1 = ex2(fmaf(s[4 * i + 1], SCL2, -f0));
            const float e2 = ex2(fmaf(s[4 * i + 2], SCL2, -f1)), e3 = ex2(fmaf(s[4 * i + 3], SCL2, -f1));
            a0 += e0; b0 += e1; a1 += e2; b1 += e3;
            pw[2 * i] = pack_bf(e0, e1); pw[2 * i + 1] = pack_bf(e2, e3);
            if (i == VREL) {
#pragma unroll
              for (int k = 0; k < 2 * VREL + 2; k++) asm volatile("" : "+r"(pw[k])::"memory");
              mbar_wait(bar_mod, 0);
              wg_wait<0>();
              mbar_arrive_cl(rempty, ODD ? 16 : 0, !redo && (ODD || j));
#pragma unroll
              for (int k = 4 * VREL + 4; k < 64; k++) asm volatile("" : "+f"(s[k])::"memory");
            }
          }
          a0 += b0; a1 += b1;
          if (redo) break;
          redo = __any_sync(0xffffffffu, !(a0 + a1 < 0x1p90f));
          if (first) {
            uint32_t m0 = __ballot_sync(0xffffffffu, a0 > 0x1p-80f), m1 = __ballot_sync(0xffffffffu, a1 > 0x1p-80f);
            m0 |= m0 >> 1; m1 |= m1 >> 1; m0 |= m0 >> 2; m1 |= m1 >> 2;
            redo = redo || (m0 & m1 & 0x11111111u) != 0x11111111u;
          }
          if (!redo) break;
        }
        l0 += a0; l1 += a1;
        keep(pw);
        keep(o);
        if (so) store_chunk<0>(o, i0, i1, qw + unit_of(qt, 0) + frag_offset(warp));
        keep(o);
        if (j == (ODD ? 5 : 0)) { fence_async_smem(); if (ODD) mbar_arrive(bar_ofull + wg * 8); }
        mbar_wait(bfull + (ODD ? 24 : 8), ph);
        bar_sync(2 + wg, 256);
        if (!last) {
          const uint32_t qn = qt >> (j >= 3 ? 8 : 0);
          wg_fence();
          issue_qk(s, qw + unit_of(qn, 0), qw + unit_of(qn, 1), base + unit_of(at, ODD ? 3 : 1));
          wg_commit();
          mbar_wait(bfull + (ODD ? 0 : 16), ODD ? ph ^ 1 : ph);
        }
        if (so) { store_chunk<1>(o, i0, i1, qw + unit_of(qt, 1) + frag_offset(warp)); keep(o); }
        wg_fence();
        issue_pv(o, pw, base + unit_of(at, ODD ? (last ? 3 : 0) : 2), !first);
        wg_commit();
        bar_arrive(3 - wg, 256);
        wg_wait<1>();
        keep(s);
        mbar_arrive_cl(rempty, ODD ? 24 : 8, !last);
        PROF(4, tid == 0 && ps == 1, 51 + j);
      };
      uint32_t pa[32], pb[32];
#pragma unroll 1
      for (int j = 0; j < 8; j += 2) {
        step(std::false_type{}, j, pa, pb);
        step(std::true_type{}, j + 1, pb, pa);
      }
      {
        const float i0 = inv_quad_sum(l0), i1 = inv_quad_sum(l1);
        wg_wait<0>();
        keep(o);
        mbar_arrive_cl(rempty, 24);
        store_chunk<0>(o, i0, i1, qw + unit_of(qt, 2) + frag_offset(warp));
        store_chunk<1>(o, i0, i1, qw + unit_of(qt, 3) + frag_offset(warp));
        fence_async_smem();
        mbar_arrive(bar_ofull + 16 + wg * 8);
      }
      PROF(2, tid == 0, 10 + ps * 8);
    }

    const int ln = fresh_lane(), g = ln >> 2, tq = ln & 3, ct = warp * 32 + ln;
    const bool lane0 = ln == 0;
    const int lrow0 = warp * 16 + g;
    const int grow0 = rb * 128 + lrow0;
    const uint32_t res = base + OFF_RES, trow = res + wg * 8192 + frag_offset(warp);
    uint32_t xr[32];
    uint4 sv[4], own;
    uint32_t* sp[4];
#pragma unroll
    for (int k = 0; k < 4; k++) sp[k] = g_stats + ((((tq >> 1) * 4 + k) ^ cj) * SEQ + grow0 + (tq & 1) * 8) * 4;
    {
      const uint64_t da = make_desc(base + wg * 8192, 16, 1024), db = make_desc(base, 8192, 1024);
      constexpr int U = UNIT / 16;
#define HALF_STAGE(acc, xu, wu) _Pragma("unroll") for (int kk = 0; kk < 4; kk++) mma_ss<1>(acc, da + (xu) * U + kk * 2, db + (wu) * U + kk * 128, 1)
      PROF(10, ct == PT, 19); STAMP(0);
      cluster_arrive();
      mbar_wait(gfull, 1);
      mbar_wait(gfull + 8, 1);
      bar_sync(2 + wg, 256);
      wg_fence();
      HALF_STAGE(o, 7, 1);
      HALF_STAGE(o, 8, 3);
      wg_commit();
      STAMP(16);
      mbar_wait(gfull + 16, 1);
      STAMP(17);
      wg_fence();
      HALF_STAGE(o, 6, 11);
      wg_commit();
      bar_arrive(3 - wg, 256);
      mbar_wait(bar_par, 0);
      uint32_t* xo = g_xch + ((size_t)b * 8 * 256 + ct) * 4;
      const uint32_t* xi = g_xch + ((size_t)(b ^ 2) * 8 * 256 + ct) * 4;
      const uint32_t par1 = (~lds1(par + PAR_CONST + 4) & 1) << 16;
      wg_wait<1>();
      mbar_arrive_pred(bar_rel, lane0);
      wg_wait<0>();
      keep(o);
      mbar_arrive_pred(bar_ring, lane0);
      PROF(8, ct == PT, 20); STAMP(1);
#define SEND(i) st_b128(xo + (i) * 1024, (pack_bf(o[8 * (i)], o[8 * (i) + 1]) & ~0x10000u) | par1, pack_bf(o[8 * (i) + 2], o[8 * (i) + 3]), \
                        pack_bf(o[8 * (i) + 4], o[8 * (i) + 5]), pack_bf(o[8 * (i) + 6], o[8 * (i) + 7]))
#pragma unroll
      for (int i = 0; i < NS1; i++) SEND(i);
      PROF(8, ct == PT, 21); STAMP(2);
      bar_sync(2 + wg, 256);
      wg_fence();
      HALF_STAGE(s, 7, 0);
      HALF_STAGE(s, 8, 2);
      HALF_STAGE(s, 6, 10);
      wg_commit();
      bar_arrive(3 - wg, 256);
      STAMP(18);
      mbar_wait(gfull + 24, 1);
#pragma unroll
      for (int i = NS1; i < 8; i++) SEND(i);
      uint4 v[8];
#pragma unroll
      for (int i = 0; i < LD1; i++) v[i] = ld_b128(xi + i * 1024);
      STAMP(19);
      mbar_wait(bar_xres, 0);
      wg_wait<0>();
      mbar_arrive_pred(bar_ring + 8, lane0);
      bar_sync(2 + wg, 256);
      STAMP(20);
#pragma unroll
      for (int i = LD1; i < LD2; i++) v[i] = ld_b128(xi + i * 1024);
      mbar_wait(bar_xres, 0);
      wg_fence();
      HALF_STAGE(s, 9, 4);
      wg_commit();
      mbar_wait(bar_rx, 0);
      wg_fence();
      HALF_STAGE(s, 1, 5);
      wg_commit();
      bar_arrive(3 - wg, 256);
      STAMP(21);
#pragma unroll
      for (int i = LD2; i < 8; i++) v[i] = ld_b128(xi + i * 1024);
      if (LD2 < 8) mbar_wait(bar_xres, 0);
      wg_wait<0>();
      keep(s);
      mbar_arrive_pred(bar_ring + 16, lane0);
      PROF(10, ct == PT, 23); STAMP(4);
#pragma unroll
      for (int i = 0; i < 16; i += 2) ldmatrix4((trow ^ ((i & 7) << 4)) + (i >> 3) * 16384, xr[2 * i], xr[2 * i + 1], xr[2 * i + 2], xr[2 * i + 3]);
      uint32_t ga[16];
      uint4 bw[8];
#pragma unroll
      for (int i = 0; i < 8; i++) {
        if (!(i & 1)) {
          const uint4 t = lds4(par + PAR_SINK + i * 32 + tq * 16);
          ga[2 * i] = t.x; ga[2 * i + 1] = t.y; ga[2 * i + 2] = t.z; ga[2 * i + 3] = t.w;
        }
        bw[i] = lds4(par + PAR_T1 + i * 64 + tq * 16);
        if (!(g & 1)) { bw[i].x = 0x3f803f80u; bw[i].y = 0x3f803f80u; }
      }
      uint32_t pk[32];
      pack_p(s, pk);
      keep(pk);
      {
        uint32_t n = 0, miss;
        do {
          miss = 0;
#pragma unroll
          for (int i = 0; i < 8; i++) miss |= v[i].x ^ par1;
          miss = __any_sync(0xffffffffu, miss & 0x10000u);
          if (miss) {
#pragma unroll
            for (int i = 0; i < 8; i++)
              asm volatile("{ .reg .pred p; .reg .b32 t; xor.b32 t, %0, %5; and.b32 t, t, 0x10000; setp.ne.u32 p, t, 0;\n"
                           "@p ld.relaxed.gpu.global.v4.u32 {%0, %1, %2, %3}, [%4]; }"
                           : "+r"(v[i].x), "+r"(v[i].y), "+r"(v[i].z), "+r"(v[i].w) : "l"(xi + i * 1024), "r"(par1) : "memory");
          }
          watchdog(n);
        } while (miss);
      }
      PROF(8, ct == PT, 22); STAMP(3);
      float ds[4] = {0.f, 0.f, 0.f, 0.f}, dl[4] = {0.f, 0.f, 0.f, 0.f}, q0[4] = {0.f, 0.f, 0.f, 0.f}, q1[4] = {0.f, 0.f, 0.f, 0.f};
#pragma unroll
      for (int i = 0; i < 8; i++) {
        const uint32_t u0 = hfma2(ga[2 * i], hadd2(pk[4 * i], v[i].x & ~0x10000u), xr[4 * i]);
        const uint32_t u1 = hfma2(ga[2 * i], hadd2(pk[4 * i + 1], v[i].y), xr[4 * i + 1]);
        const uint32_t u2 = hfma2(ga[2 * i + 1], hadd2(pk[4 * i + 2], v[i].z), xr[4 * i + 2]);
        const uint32_t u3 = hfma2(ga[2 * i + 1], hadd2(pk[4 * i + 3], v[i].w), xr[4 * i + 3]);
        xr[4 * i] = u0; xr[4 * i + 1] = u1; xr[4 * i + 2] = u2; xr[4 * i + 3] = u3;
        mma16816(ds, u0, u1, u2, u3, bw[i].x, bw[i].y);
        mma16816(dl, u0, u1, u2, u3, bw[i].z, bw[i].w);
        mma16816(q0, u0, u1, u2, u3, u0, u2);
        mma16816(q1, u0, u1, u2, u3, u1, u3);
      }
      const float sqa = __shfl_sync(0xffffffffu, (g & 1) ? q0[1] : q0[0], g * 4 + (g >> 1));
      const float sqb = __shfl_sync(0xffffffffu, (g & 1) ? q1[3] : q1[2], g * 4 + (g >> 1));
      own = (tq & 1) ? make_uint4(__float_as_uint(ds[2]), __float_as_uint(sqb), __float_as_uint(ds[3] + dl[3]), tag)
                                 : make_uint4(__float_as_uint(ds[0]), __float_as_uint(sqa), __float_as_uint(ds[1] + dl[1]), tag);
      if (tq < 2) st_b128(sp[0], own.x, own.y, own.z, own.w);
#pragma unroll
      for (int k = 0; k < 4; k++) sv[k] = make_uint4(0, 0, 0, 0);
    }
    PROF(8, ct == PT, 29); STAMP(5);
    uint32_t mm, ih, il;
    float rbest;
    uint32_t wf[128];
    const uint32_t frow = (ln & 7) + (ln >> 4) * 8;
    const uint32_t wfo = base + (warp & 1) * 8192 + frow * 64 + ((((ln >> 3) & 1) ^ ((frow >> 1) & 3)) << 4);
#define LOAD_WF(m) _Pragma("unroll") for (int f = 0; f < 16; f++) {                                                   \
      const int r = ((f >> 1) * 4 + (m) * 2 + (f & 1)) * 4;                                                           \
      ldmatrix4t(((wfo + unit_of((m) ? FT_U : FT_G, warp >> 1)) ^ ((f & 1) * 32)) + (f >> 1) * 1024, wf[r], wf[r + 1], wf[r + 2], wf[r + 3]); \
    }
    bool early;
    {
#pragma unroll
      for (int i = 0; i < 16; i += 2) stmatrix4((trow ^ ((i & 7) << 4)) + (i >> 3) * 16384, xr[2 * i], xr[2 * i + 1], xr[2 * i + 2], xr[2 * i + 3]);
      const uint4 cst = lds4(par + PAR_CONST);
      const float A1 = __uint_as_float(cst.x), A2 = __uint_as_float(cst.z);
      uint32_t n = 0;
      early = false;
#pragma unroll 1
      while (true) {
        uint32_t miss;
        asm volatile("{ .reg .pred p0, p1, p2, p3; .reg .b64 u, v; .reg .b128 w;\n"
                     "setp.ge.u32 p0, %22, 2; setp.ne.and.u32 p0, %4, %21, p0; setp.ne.u32 p1, %8, %21; setp.ne.u32 p2, %12, %21; setp.ne.u32 p3, %16, %21;\n"
                     "@p0 ld.relaxed.gpu.global.v4.u32 {%1, %2, %3, %4}, [%17];\n"
                     "@p1 ld.relaxed.gpu.global.v4.u32 {%5, %6, %7, %8}, [%18];\n"
                     "@p2 ld.relaxed.gpu.global.v4.u32 {%9, %10, %11, %12}, [%19];\n"
                     "@p3 ld.relaxed.gpu.global.v4.u32 {%13, %14, %15, %16}, [%20];\n"
                     "or.pred p0, p0, p1; or.pred p2, p2, p3; or.pred p0, p0, p2; vote.sync.any.pred p0, p0, 0xffffffff; selp.u32 %0, 1, 0, p0; }"
                     : "=r"(miss), "+r"(sv[0].x), "+r"(sv[0].y), "+r"(sv[0].z), "+r"(sv[0].w), "+r"(sv[1].x), "+r"(sv[1].y), "+r"(sv[1].z), "+r"(sv[1].w),
                       "+r"(sv[2].x), "+r"(sv[2].y), "+r"(sv[2].z), "+r"(sv[2].w), "+r"(sv[3].x), "+r"(sv[3].y), "+r"(sv[3].z), "+r"(sv[3].w)
                     : "l"(sp[0]), "l"(sp[1]), "l"(sp[2]), "l"(sp[3]), "r"(tag), "r"(tq) : "memory");
        if (!miss) break;
        if (!early && (b >= NFFN || __all_sync(0xffffffffu, mbar_test(bar_box + (warp >> 1) * 8, 0)))) {
          early = true;
          LOAD_WF(0);
          __syncwarp();
          mbar_arrive_pred(bar_gate, lane0);
        }
        watchdog(n);
      }
      const uint4 v0 = tq < 2 ? own : sv[0], v1 = sv[1], v2 = sv[2], v3 = sv[3];
      PROF(8, ct == PT, 30); STAMP(6);
      float su = (__uint_as_float(v0.x) + __uint_as_float(v1.x)) + (__uint_as_float(v2.x) + __uint_as_float(v3.x));
      float sq = (__uint_as_float(v0.y) + __uint_as_float(v1.y)) + (__uint_as_float(v2.y) + __uint_as_float(v3.y));
      float dt = (__uint_as_float(v0.z) + __uint_as_float(v1.z)) + (__uint_as_float(v2.z) + __uint_as_float(v3.z));
      su += __shfl_xor_sync(0xffffffffu, su, 2); sq += __shfl_xor_sync(0xffffffffu, sq, 2); dt += __shfl_xor_sync(0xffffffffu, dt, 2);
      const float m = su * (1.f / DM);
      float mb, sd;
      ln_scalars(m, fmaxf(sq * (1.f / DM) - m * m, 0.f), mb, sd);
      const float inv = rcp(sd);
      rbest = (dt - mb * A1) * inv + A2;
      mm = pack_bf(mb, mb);
      ih = pack_bf(inv, inv);
      const float lo = inv - bf_lo(ih);
      il = pack_bf(lo, lo);
    }
    int ibest;
    {
      const uint32_t bits = __float_as_uint(rbest);
      const uint32_t key = (((int)bits < 0 ? ~bits : bits | 0x80000000u) & ~0x1ffu) | ((127 - lrow0 - (tq & 1) * 8) << 2) | tag;
      sts1(par + PAR_RED + warp * 4, __reduce_max_sync(0xffffffffu, key));
      PROF(8, ct == PT, 38); STAMP(7);
      bar_sync(1, 256);
      const uint4 ka = lds4(par + PAR_RED), kb = lds4(par + PAR_RED + 16);
      const uint32_t k2 = max(max(max(ka.x, ka.y), max(ka.z, ka.w)), max(max(kb.x, kb.y), max(kb.z, kb.w)));
      if (ct == 0 && cj == 0) st_relaxed(g_cand + rb, k2);
      ibest = 127 - ((k2 >> 2) & 127);
    }
    PROF(8, ct == PT, 39); STAMP(8);
    if ((ibest >> 4) == warp) {
      const int src = (ibest & 7) * 4 + ((ibest >> 3) & 1), ch = g * 2;
      const uint32_t cm = __shfl_sync(0xffffffffu, mm, src), ch_ = __shfl_sync(0xffffffffu, ih, src), cl = __shfl_sync(0xffffffffu, il, src);
      const uint32_t xa = res + (ch >> 3) * 16384 + ibest * 128 + (((ch & 7) ^ (ibest & 7)) << 4) + tq * 4;
      const uint32_t x0 = lds1(xa), x1 = lds1(xa ^ 16);
      const uint2 p0 = lds2(par + PAR_T2 + ch * 64 + tq * 16), p1 = lds2(par + PAR_T2 + ch * 64 + 64 + tq * 16);
      uint32_t* dst = g_row + rb * 2 * DM + cj * 128 + ln * 4;
      st_pairs(dst, ln_mod(x0, cm, ch_, cl, p0.x, p0.y), ln_mod(x1, cm, ch_, cl, p1.x, p1.y), tag);
      st_pairs(dst + DM, x0, x1, tag);
      __syncwarp();
    }
    PROF(8, ct == PT, 37); STAMP(9);
    uint32_t wd[64];
    const uint32_t wda = base + unit_of(FT_D, warp >> 1) + (warp & 1) * 8192 + frow * 128 + ((((ln >> 3) & 1) ^ (ln & 7)) << 4);
#define LOAD_WD(f) ldmatrix4t((wda ^ ((((f) >> 1) & 3) * 32)) + ((f) >> 3) * 4096 + ((f) & 1) * 2048, wd[4 * (f)], wd[4 * (f) + 1], wd[4 * (f) + 2], wd[4 * (f) + 3])
    if (!early) {
      if (b < NFFN) mbar_wait(bar_box + (warp >> 1) * 8, 0);
      LOAD_WF(0);
      __syncwarp();
      mbar_arrive_pred(bar_gate, lane0);
    }
    if (b < NFFN) {
      const uint32_t own = base + unit_of(FT_G, warp >> 1) + (warp & 1) * 8192;
      mbar_wait(bar_box + (4 + (warp >> 1)) * 8, 0);
      LOAD_WF(1);
      uint32_t* const ydst = g_ypart + ((size_t)(warp * 16 + tq * 2) * NFFN + b) * 8 + g;
      PROF(8, ct == PT, 31); STAMP(10);
      bool wdok;
      {
        uint32_t n = 0;
        while (!(wdok = __all_sync(0xffffffffu, mbar_test(bar_box + (8 + (warp >> 1)) * 8, 0))) && !__all_sync(0xffffffffu, mbar_test(bar_sel, 0))) watchdog(n);
      }
      if (wdok) {
#pragma unroll
        for (int f = 0; f < 16; f++) LOAD_WD(f);
      }
      STAMP(11);
      mbar_wait(bar_sel, 0);
      PROF(8, ct == PT, 33); STAMP(12);
      float d[8][4];
#pragma unroll
      for (int i = 0; i < 4; i++) { d[i][0] = 0.f; d[i][1] = 0.f; d[i][2] = 0.f; d[i][3] = 0.f; }
#pragma unroll
      for (int ks = 0; ks < 8; ks++) {
        const uint2 hb = lds2(own + 256 + ks * 32 + tq * 8);
#pragma unroll
        for (int mt = 0; mt < 4; mt++) {
          const int r = ks * 16 + mt * 4;
          mma16816(d[mt], wf[r], wf[r + 1], wf[r + 2], wf[r + 3], hb.x, hb.y);
        }
      }
      sts2(own + (tq * 8 + g) * 8, __float_as_uint((tq & 2) ? ((tq & 1) ? d[1][2] : d[1][0]) : ((tq & 1) ? d[0][2] : d[0][0])),
           __float_as_uint((tq & 2) ? ((tq & 1) ? d[3][2] : d[3][0]) : ((tq & 1) ? d[2][2] : d[2][0])));
      bar_sync(1, 256);
      uint32_t ab[4];
      {
        float G = 0.f, U = 0.f;
        uint2 pv[8];
#pragma unroll
        for (int w8 = 0; w8 < 8; w8++) pv[w8] = lds2(base + ln * 8 + ((FT_G >> (w8 >> 1) * 4) & 15) * UNIT + (w8 & 1) * 8192);
#pragma unroll
        for (int w8 = 0; w8 < 8; w8 += 2) {
          G += __uint_as_float(pv[w8].x) + __uint_as_float(pv[w8 + 1].x);
          U += __uint_as_float(pv[w8].y) + __uint_as_float(pv[w8 + 1].y);
        }
        const float act = rbf(silu_f(rbf(G))) * rbf(U);
        const uint32_t pk = pack_bf(act, __shfl_down_sync(0xffffffffu, act, 1));
#pragma unroll
        for (int i = 0; i < 4; i++) ab[i] = __shfl_sync(0xffffffffu, pk, i * 8 + tq * 2);
      }
      if (!wdok) {
        mbar_wait(bar_box + (8 + (warp >> 1)) * 8, 0);
#pragma unroll
        for (int f = 0; f < 16; f++) LOAD_WD(f);
      }
      PROF(8, ct == PT, 34); STAMP(13);
#pragma unroll
      for (int mt = 0; mt < 8; mt++) {
        d[mt][0] = 0.f; d[mt][1] = 0.f; d[mt][2] = 0.f; d[mt][3] = 0.f;
        mma16816(d[mt], wd[mt * 8], wd[mt * 8 + 1], wd[mt * 8 + 2], wd[mt * 8 + 3], ab[0], ab[1]);
        mma16816(d[mt], wd[mt * 8 + 4], wd[mt * 8 + 5], wd[mt * 8 + 6], wd[mt * 8 + 7], ab[2], ab[3]);
      }
#pragma unroll
      for (int i = 0; i < 4; i++) {
        const int m4 = (i >> 1) * 4, e = (i & 1) * 2;
        const float y = (tq & 2) ? ((tq & 1) ? d[m4 + 3][e] : d[m4 + 2][e]) : ((tq & 1) ? d[m4 + 1][e] : d[m4][e]);
        st_relaxed(ydst + (m4 * 2 + (i & 1)) * NFFN * 8, tagf(y, tag));
      }
      PROF(8, ct == PT, 35); STAMP(14);
    }
    mbar_wait(bar_sel, 0);
    mbar_arrive_pred(bar_win, ct == 0);
    const int iwin = lds1(par + PAR_CONST + 60) & 0x7ff;
    const bool cand = (iwin >> 4) == rb * 8 + warp;
    {
      const uint32_t mm0 = __shfl_sync(0xffffffffu, mm, ln & ~1), mm1 = __shfl_sync(0xffffffffu, mm, ln | 1);
      const uint32_t ih0 = __shfl_sync(0xffffffffu, ih, ln & ~1), ih1 = __shfl_sync(0xffffffffu, ih, ln | 1);
      const uint32_t il0 = __shfl_sync(0xffffffffu, il, ln & ~1), il1 = __shfl_sync(0xffffffffu, il, ln | 1);
#pragma unroll 1
      for (int hf = 0; hf < 2; hf++) {
        uint32_t x[16];
#pragma unroll
        for (int i = 0; i < 8; i += 2) ldmatrix4((trow ^ (i << 4)) + hf * 16384, x[2 * i], x[2 * i + 1], x[2 * i + 2], x[2 * i + 3]);
#pragma unroll
        for (int i = 0; i < 8; i++) {
          const uint4 pv = lds4(par + PAR_T2 + (hf * 8 + i) * 64 + tq * 16);
          x[2 * i] = hadd2(x[2 * i], hmul2(pv.z, ln_mod(x[2 * i], mm0, ih0, il0, pv.x, pv.y)));
          x[2 * i + 1] = hadd2(x[2 * i + 1], hmul2(pv.z, ln_mod(x[2 * i + 1], mm1, ih1, il1, pv.x, pv.y)));
        }
#pragma unroll
        for (int i = 0; i < 8; i += 2) stmatrix4((trow ^ (i << 4)) + hf * 16384, x[2 * i], x[2 * i + 1], x[2 * i + 2], x[2 * i + 3]);
      }
      if (!cand) fence_async_smem();
      __syncwarp();
      if (!cand && elect_one()) {
        tma2d_store(&maps.out, res + warp * 2048, cj * 128, rb * 128 + warp * 16);
        tma2d_store(&maps.out, res + 16384 + warp * 2048, cj * 128 + 64, rb * 128 + warp * 16);
        asm volatile("cp.async.bulk.commit_group;" ::: "memory");
      }
    }
    if (cand) {
      const int wrow0 = warp * 16;
#pragma unroll 2
      for (int p = 0; p < 8; p++) {
        const int row = 2 * p + (ln >> 4), ch = ln & 15;
        const uint4 v = lds4(res + (ch >> 3) * 16384 + (wrow0 + row) * 128 + (((ch & 7) ^ (row & 7)) << 4));
        if (rb * 128 + wrow0 + row != iwin) *reinterpret_cast<uint4*>(P.out + (size_t)(rb * 128 + wrow0 + row) * DM + cj * 128 + ch * 8) = v;
      }
    }
    asm volatile("cp.async.bulk.wait_group.read 0;" ::: "memory");
    PROF(8, ct == PT, 11); STAMP(15);
    cluster_wait();
  }
}

typedef CUresult (*EncodeFn)(CUtensorMap*, CUtensorMapDataType, cuuint32_t, void*, const cuuint64_t*, const cuuint64_t*,
                             const cuuint32_t*, const cuuint32_t*, CUtensorMapInterleave, CUtensorMapSwizzle,
                             CUtensorMapL2promotion, CUtensorMapFloatOOBfill);

void map2d(EncodeFn enc, CUtensorMap* m, const void* p, uint64_t rows, uint64_t cols, uint32_t brows) {
  cuuint64_t dims[2] = {cols, rows}, strides[1] = {cols * 2};
  cuuint32_t box[2] = {64, brows}, es[2] = {1, 1};
  enc(m, CU_TENSOR_MAP_DATA_TYPE_BFLOAT16, 2, const_cast<void*>(p), dims, strides, box, es, CU_TENSOR_MAP_INTERLEAVE_NONE,
      CU_TENSOR_MAP_SWIZZLE_128B, CU_TENSOR_MAP_L2_PROMOTION_L2_256B, CU_TENSOR_MAP_FLOAT_OOB_FILL_NONE);
}
void map2d_narrow(EncodeFn enc, CUtensorMap* m, const void* p, uint64_t rows, uint64_t cols, uint32_t brows) {
  cuuint64_t dims[2] = {cols, rows}, strides[1] = {cols * 2};
  cuuint32_t box[2] = {32, brows}, es[2] = {1, 1};
  enc(m, CU_TENSOR_MAP_DATA_TYPE_BFLOAT16, 2, const_cast<void*>(p), dims, strides, box, es, CU_TENSOR_MAP_INTERLEAVE_NONE,
      CU_TENSOR_MAP_SWIZZLE_64B, CU_TENSOR_MAP_L2_PROMOTION_L2_64B, CU_TENSOR_MAP_FLOAT_OOB_FILL_NONE);
}
void map3d(EncodeFn enc, CUtensorMap* m, const void* p, uint64_t rows, uint64_t cols, uint32_t brows, uint32_t nch) {
  cuuint64_t dims[3] = {64, rows, cols / 64}, strides[2] = {cols * 2, 128};
  cuuint32_t box[3] = {64, brows, nch}, es[3] = {1, 1, 1};
  enc(m, CU_TENSOR_MAP_DATA_TYPE_BFLOAT16, 3, const_cast<void*>(p), dims, strides, box, es, CU_TENSOR_MAP_INTERLEAVE_NONE,
      CU_TENSOR_MAP_SWIZZLE_128B, CU_TENSOR_MAP_L2_PROMOTION_L2_256B, CU_TENSOR_MAP_FLOAT_OOB_FILL_NONE);
}

}

extern "C" void kernel_launch(void* const* d_in, const int* in_sizes, int n_in, void* d_out, int out_size) {
  (void)in_sizes; (void)n_in; (void)out_size;
  static EncodeFn enc = nullptr;
  if (!enc) {
    void* fn = nullptr;
    cudaDriverEntryPointQueryResult st;
    cudaGetDriverEntryPoint("cuTensorMapEncodeTiled", &fn, cudaEnableDefault, &st);
    enc = (EncodeFn)fn;
    cudaFuncSetAttribute(fused_kernel, cudaFuncAttributeMaxDynamicSharedMemorySize, SMEM_BYTES);
  }
  Maps maps;
  map2d(enc, &maps.x, d_in[0], SEQ, DM, 128);
  map2d(enc, &maps.out, d_out, SEQ, DM, 16);
  map3d(enc, &maps.wq, d_in[3], DM, NQ, 64, 2);
  map3d(enc, &maps.k, d_in[1], 4 * SK, 128, 128, 1);
  map3d(enc, &maps.v, d_in[2], 4 * SK, 128, 128, 1);
  map3d(enc, &maps.wo, d_in[4], NQ, DM, 64, 2);
  map2d_narrow(enc, &maps.wg, d_in[7], DM, FF, 256);
  map2d_narrow(enc, &maps.wu, d_in[8], DM, FF, 256);
  map3d(enc, &maps.wd, d_in[9], FF, DM, 32, 4);
  map2d_narrow(enc, &maps.wm, d_in[11], DM, NMOD, 256);
  Ptrs p;
  p.x = (const __nv_bfloat16*)d_in[0];
  p.w_r = (const __nv_bfloat16*)d_in[6];
  p.w_gate = (const __nv_bfloat16*)d_in[7];
  p.w_up = (const __nv_bfloat16*)d_in[8];
  p.w_down = (const __nv_bfloat16*)d_in[9];
  p.c = (const __nv_bfloat16*)d_in[10];
  p.w_mod = (const __nv_bfloat16*)d_in[11];
  p.out = (__nv_bfloat16*)d_out;
  fused_kernel<<<NMAIN + NHELP, 384, SMEM_BYTES>>>(maps, p);
}
```

```cpp
#include <cuda_runtime.h>
#include <cuda_bf16.h>
#include <cuda.h>
#include <stdint.h>
#include <type_traits>

#define HD 2
#define HDX 2
#define NRS 8
#define FPACE 3
#define GOST 20
#define WB 2
#define WN 20
#define RES0 17
#define RES1 20
#define HU 32
#define NS1 5
#define PG0 15
#define PSL 0
#define FB0 0
#define FB2 8
#define OPS 8192
#define OFL 0
#define ODS 8
#define MODUL hfma2
#define ODS1 5
#define LD1 0
#define LD2 4
#define FB1 2
#define FPB 8
#define FPACE0 2
#define OSL 900
#define OSL2 400
#define VREL 5
#define E0 3

namespace {

constexpr int SEQ = 2048, DM = 1024, NQ = 4096, SK = 2048, WIN = 512, FF = 3584, NMOD = 6144;
constexpr int NMAIN = 128, NHELP = 4, NFFN = 112;
constexpr int NSLOT = 4, SLOT_BYTES = 32768, UNIT = 16384, GST_BYTES = 3 * UNIT;
constexpr uint32_t XT1 = 0xDCBA, XT2 = 0x9687;
constexpr uint32_t WT0 = 0xA741, WT1 = 0x7420, WT2 = 0x4A20;
constexpr uint32_t AT0 = WT1, AT1 = WT2;
constexpr uint32_t QT = 0xDC9696DC;
constexpr int OFF_STAGE = 12 * UNIT;
constexpr uint32_t FT_G = 0x07B3, FT_U = 0xA628, FT_D = 0x5149;
constexpr int OFF_RES = 12 * UNIT;
constexpr int OFF_PAR = 14 * UNIT;
constexpr int OFF_BAR = OFF_PAR + 2528;
constexpr int SMEM_BYTES = OFF_BAR + 544;
static_assert(SMEM_BYTES <= 232448, "smem");

constexpr int PAR_T1 = 0;
constexpr int PAR_T2 = 512;
constexpr int PAR_CONST = 1536;
constexpr int PAR_RED = 1600;
constexpr int PAR_SINK = 2176;

struct Maps {
  CUtensorMap x, wq, k, v, wo, wg, wu, wd, wm, out;
};
struct Ptrs {
  const __nv_bfloat16 *x, *w_r, *c, *w_mod, *w_gate, *w_up, *w_down;
  __nv_bfloat16* out;
};

__device__ __align__(1024) uint8_t g_act[16 * 80 * UNIT];
__device__ __align__(128) uint32_t g_mod[NMOD];
__device__ __align__(128) uint32_t g_modp[2 * 2 * DM];
__device__ __align__(128) uint32_t g_ln1[SEQ * 4];
__device__ __align__(128) uint32_t g_cnt_h[16 * 32];
__device__ __align__(128) uint32_t g_cnt_o[128 * 32];
__device__ __align__(128) uint32_t g_xch[NMAIN * 8 * 256 * 4];
__device__ __align__(128) uint32_t g_stats[8 * SEQ * 4];
__device__ __align__(128) uint32_t g_cand[32];
__device__ __align__(128) uint32_t g_row[16 * 2 * DM];
__device__ __align__(128) uint32_t g_ypart[NMAIN * NFFN * 8];
__device__ uint32_t g_epoch;

__device__ __forceinline__ uint32_t fresh_lane() { uint32_t l; asm volatile("mov.u32 %0, %%laneid;" : "=r"(l)); return l; }
__device__ __forceinline__ uint32_t frag_offset(int warp) {
  const uint32_t l = fresh_lane();
  return ((warp & 3) * 16 + (l & 15)) * 128 + (((l >> 4) ^ (l & 7)) << 4);
}
__device__ __forceinline__ bool elect_one() {
  uint32_t p;
  asm volatile("{ .reg .pred q; elect.sync _|q, 0xffffffff; selp.u32 %0, 1, 0, q; }" : "=r"(p));
  return p;
}
__device__ __forceinline__ uint32_t smem_u32(const void* p) { return (uint32_t)__cvta_generic_to_shared(p); }
__device__ __forceinline__ void mbar_init(uint32_t bar, uint32_t cnt) {
  asm volatile("mbarrier.init.shared::cta.b64 [%0], %1;" ::"r"(bar), "r"(cnt) : "memory");
}
__device__ __forceinline__ void mbar_expect_tx(uint32_t bar, uint32_t bytes) {
  asm volatile("mbarrier.arrive.expect_tx.shared::cta.b64 _, [%0], %1;" ::"r"(bar), "r"(bytes) : "memory");
}
__device__ __forceinline__ void mbar_arrive(uint32_t bar) {
  asm volatile("mbarrier.arrive.shared::cta.b64 _, [%0];" ::"r"(bar) : "memory");
}
__device__ __forceinline__ void mbar_arrive_pred(uint32_t bar, bool p) {
  asm volatile("{ .reg .pred p; setp.ne.b32 p, %1, 0; @p mbarrier.arrive.shared::cta.b64 _, [%0]; }" ::"r"(bar), "r"((int)p) : "memory");
}
__device__ __forceinline__ void mbar_arrive_cl(uint32_t bar, uint32_t off, bool p = true) {
  asm volatile("{ .reg .pred p, q; .reg .b32 a; setp.ne.b32 q, %2, 0; setp.ne.and.b32 p, %0, 0, q; add.u32 a, %0, %1; @p mbarrier.arrive.shared::cluster.b64 _, [a]; }"
               ::"r"(bar), "r"(off), "r"((int)p) : "memory");
}
__device__ __forceinline__ uint32_t mapa(uint32_t addr, uint32_t cta) {
  uint32_t r; asm("mapa.shared::cluster.u32 %0, %1, %2;" : "=r"(r) : "r"(addr), "r"(cta)); return r;
}
__device__ __forceinline__ void cluster_arrive() { asm volatile("barrier.cluster.arrive.relaxed.aligned;" ::: "memory"); }
__device__ __forceinline__ void cluster_wait() { asm volatile("barrier.cluster.wait.aligned;" ::: "memory"); }
__device__ __forceinline__ void watchdog(uint32_t& n) {
}
__device__ __forceinline__ void mbar_wait(uint32_t bar, uint32_t parity) {
  asm volatile("{\n.reg .pred p;\nWAIT_%=:\nmbarrier.try_wait.parity.shared::cta.b64 p, [%0], %1;\n@!p bra WAIT_%=;\n}" ::"r"(bar), "r"(parity) : "memory");
}
__device__ __forceinline__ bool mbar_test(uint32_t bar, uint32_t parity) {
  uint32_t ok;
  asm volatile("{\n.reg .pred p;\nmbarrier.test_wait.parity.shared::cta.b64 p, [%1], %2;\nselp.u32 %0, 1, 0, p;\n}" : "=r"(ok) : "r"(bar), "r"(parity) : "memory");
  return ok;
}
__device__ __forceinline__ uint64_t l2_stream() {
  uint64_t f; asm("createpolicy.fractional.L2::evict_first.b64 %0, 1.0;" : "=l"(f)); return f;
}
__device__ __forceinline__ void tma2d(uint32_t dst, const CUtensorMap* m, int c0, int c1, uint32_t bar) {
  asm volatile("cp.async.bulk.tensor.2d.shared::cluster.global.mbarrier::complete_tx::bytes.L2::cache_hint [%0], [%1, {%3, %4}], [%2], %5;"
               ::"r"(dst), "l"(m), "r"(bar), "r"(c0), "r"(c1), "l"(l2_stream()) : "memory");
}
__device__ __forceinline__ void bulk_load(uint32_t dst, const void* src, uint32_t bytes, uint32_t bar) {
  asm volatile("cp.async.bulk.shared::cluster.global.mbarrier::complete_tx::bytes [%0], [%1], %2, [%3];" ::"r"(dst), "l"(src), "r"(bytes), "r"(bar) : "memory");
}
__device__ __forceinline__ void bulk_load_stream(uint32_t dst, const void* src, uint32_t bytes, uint32_t bar) {
  asm volatile("cp.async.bulk.shared::cluster.global.mbarrier::complete_tx::bytes.L2::cache_hint [%0], [%1], %2, [%3], %4;"
               ::"r"(dst), "l"(src), "r"(bytes), "r"(bar), "l"(l2_stream()) : "memory");
}
__device__ __forceinline__ void tma2d_store(const CUtensorMap* m, uint32_t src, int c0, int c1) {
  asm volatile("cp.async.bulk.tensor.2d.global.shared::cta.bulk_group [%0, {%2, %3}], [%1];" ::"l"(m), "r"(src), "r"(c0), "r"(c1) : "memory");
}
__device__ __forceinline__ void bulk_store(void* dst, uint32_t src, uint32_t bytes) {
  asm volatile("cp.async.bulk.global.shared::cta.bulk_group [%0], [%1], %2;" ::"l"(dst), "r"(src), "r"(bytes) : "memory");
}
__device__ __forceinline__ int slice_of(int i) { return i + ((i & 7) == 1) - ((i & 7) == 2); }
__device__ __forceinline__ uint32_t unit_of(uint32_t table, uint32_t i) { return ((table >> (i * 4)) & 15) * UNIT; }
__device__ __forceinline__ void tma3d(uint32_t dst, const CUtensorMap* m, int c0, int c1, int c2, uint32_t bar) {
  asm volatile("cp.async.bulk.tensor.3d.shared::cluster.global.mbarrier::complete_tx::bytes.L2::cache_hint [%0], [%1, {%3, %4, %5}], [%2], %6;"
               ::"r"(dst), "l"(m), "r"(bar), "r"(c0), "r"(c1), "r"(c2), "l"(l2_stream()) : "memory");
}
template <bool STREAM>
__device__ __forceinline__ void tma3d_mc(uint32_t dst, const CUtensorMap* m, int c0, int c1, int c2, uint32_t bar) {
  if (STREAM)
    asm volatile("cp.async.bulk.tensor.3d.shared::cluster.global.mbarrier::complete_tx::bytes.multicast::cluster.L2::cache_hint [%0], [%1, {%3, %4, %5}], [%2], %6, %7;"
                 ::"r"(dst), "l"(m), "r"(bar), "r"(c0), "r"(c1), "r"(c2), "h"((uint16_t)3), "l"(l2_stream()) : "memory");
  else
    asm volatile("cp.async.bulk.tensor.3d.shared::cluster.global.mbarrier::complete_tx::bytes.multicast::cluster [%0], [%1, {%3, %4, %5}], [%2], %6;"
                 ::"r"(dst), "l"(m), "r"(bar), "r"(c0), "r"(c1), "r"(c2), "h"((uint16_t)3) : "memory");
}
__device__ __forceinline__ void prefetch_map(const CUtensorMap* m) {
  asm volatile("prefetch.tensormap [%0];" ::"l"(m) : "memory");
}
__device__ __forceinline__ void fence_async() { asm volatile("fence.proxy.async.global;" ::: "memory"); }
__device__ __forceinline__ void fence_async_smem() { asm volatile("fence.proxy.async.shared::cta;" ::: "memory"); }
__device__ __forceinline__ void bar_sync(int id, int n) { asm volatile("bar.sync %0, %1;" ::"r"(id), "r"(n) : "memory"); }
__device__ __forceinline__ void bar_arrive(int id, int n) { asm volatile("bar.arrive %0, %1;" ::"r"(id), "r"(n) : "memory"); }
__device__ __forceinline__ void wg_fence() { asm volatile("wgmma.fence.sync.aligned;" ::: "memory"); }
__device__ __forceinline__ void wg_commit() { asm volatile("wgmma.commit_group.sync.aligned;" ::: "memory"); }
template <int N> __device__ __forceinline__ void wg_wait() { asm volatile("wgmma.wait_group.sync.aligned %0;" ::"n"(N) : "memory"); }
__device__ __forceinline__ uint64_t make_desc(uint32_t addr, uint32_t lbo, uint32_t sbo) {
  return (uint64_t)((addr & 0x3FFFF) >> 4) | ((uint64_t)(lbo >> 4) << 16) | ((uint64_t)(sbo >> 4) << 32) | (1ull << 62);
}
__device__ __forceinline__ uint32_t ld_relaxed(const uint32_t* p) {
  uint32_t v; asm volatile("ld.relaxed.gpu.global.u32 %0, [%1];" : "=r"(v) : "l"(p) : "memory"); return v;
}
__device__ __forceinline__ uint32_t ld_acquire(const uint32_t* p) {
  uint32_t v; asm volatile("ld.acquire.gpu.global.u32 %0, [%1];" : "=r"(v) : "l"(p) : "memory"); return v;
}
__device__ __forceinline__ uint4 ld_relaxed4(const uint32_t* p) {
  uint4 v; asm volatile("ld.relaxed.gpu.global.v4.u32 {%0,%1,%2,%3}, [%4];" : "=r"(v.x), "=r"(v.y), "=r"(v.z), "=r"(v.w) : "l"(p) : "memory"); return v;
}
__device__ __forceinline__ uint2 ld_relaxed2(const uint32_t* p) {
  uint2 v; asm volatile("ld.relaxed.gpu.global.v2.u32 {%0,%1}, [%2];" : "=r"(v.x), "=r"(v.y) : "l"(p) : "memory"); return v;
}
__device__ __forceinline__ void st_relaxed(uint32_t* p, uint32_t v) {
  asm volatile("st.relaxed.gpu.global.u32 [%0], %1;" ::"l"(p), "r"(v) : "memory");
}
__device__ __forceinline__ void st_relaxed2(uint32_t* p, uint32_t a, uint32_t b) {
  asm volatile("st.relaxed.gpu.global.v2.u32 [%0], {%1,%2};" ::"l"(p), "r"(a), "r"(b) : "memory");
}
__device__ __forceinline__ void st_relaxed4(uint32_t* p, uint32_t a, uint32_t b, uint32_t c, uint32_t d) {
  asm volatile("st.relaxed.gpu.global.v4.u32 [%0], {%1,%2,%3,%4};" ::"l"(p), "r"(a), "r"(b), "r"(c), "r"(d) : "memory");
}
__device__ __forceinline__ void st_b128(uint32_t* p, uint32_t a, uint32_t b, uint32_t c, uint32_t d) {
  asm volatile("{ .reg .b64 u, v; .reg .b128 w; mov.b64 u, {%1, %2}; mov.b64 v, {%3, %4}; mov.b128 w, {u, v}; st.relaxed.gpu.global.b128 [%0], w; }"
               ::"l"(p), "r"(a), "r"(b), "r"(c), "r"(d) : "memory");
}
__device__ __forceinline__ uint4 ld_b128(const uint32_t* p) {
  uint4 r;
  asm volatile("{ .reg .b64 u, v; .reg .b128 w; ld.relaxed.gpu.global.b128 w, [%4]; mov.b128 {u, v}, w; mov.b64 {%0, %1}, u; mov.b64 {%2, %3}, v; }"
               : "=r"(r.x), "=r"(r.y), "=r"(r.z), "=r"(r.w) : "l"(p) : "memory");
  return r;
}
__device__ __forceinline__ void st_pairs(uint32_t* p, uint32_t a, uint32_t b, uint32_t tag) {
  asm volatile("{ .reg .b64 u, v; mov.b64 u, {%1, %3}; mov.b64 v, {%2, %3}; st.relaxed.gpu.global.v2.b64 [%0], {u, v}; }"
               ::"l"(p), "r"(a), "r"(b), "r"(tag) : "memory");
}
__device__ __forceinline__ uint4 ld_pairs(const uint32_t* p) {
  uint4 v;
  asm volatile("{ .reg .b64 u, v; ld.relaxed.gpu.global.v2.b64 {u, v}, [%4]; mov.b64 {%0, %1}, u; mov.b64 {%2, %3}, v; }"
               : "=r"(v.x), "=r"(v.y), "=r"(v.z), "=r"(v.w) : "l"(p) : "memory");
  return v;
}
__device__ __forceinline__ uint2 ld_pair(const uint32_t* p) {
  uint2 v;
  asm volatile("{ .reg .b64 u; ld.relaxed.gpu.global.b64 u, [%2]; mov.b64 {%0, %1}, u; }" : "=r"(v.x), "=r"(v.y) : "l"(p) : "memory");
  return v;
}
__device__ __forceinline__ void red_release(uint32_t* p, uint32_t v) {
  asm volatile("red.release.gpu.global.add.u32 [%0], %1;" ::"l"(p), "r"(v) : "memory");
}
__device__ __forceinline__ uint32_t ldg_nc1(const void* p) {
  uint32_t v;
  asm volatile("ld.global.nc.u32 %0, [%1];" : "=r"(v) : "l"(p));
  return v;
}
__device__ __forceinline__ uint4 ldg_nc4(const void* p) {
  uint4 v; asm volatile("ld.global.nc.L1::no_allocate.v4.u32 {%0,%1,%2,%3}, [%4];" : "=r"(v.x), "=r"(v.y), "=r"(v.z), "=r"(v.w) : "l"(p)); return v;
}
__device__ __forceinline__ uint4 ldg_stream4(const void* p) {
  uint4 v;
  asm volatile("ld.global.nc.L1::no_allocate.L2::cache_hint.v4.u32 {%0,%1,%2,%3}, [%4], %5;" : "=r"(v.x), "=r"(v.y), "=r"(v.z), "=r"(v.w) : "l"(p), "l"(l2_stream()));
  return v;
}
__device__ __forceinline__ void stg4(void* p, uint4 v) {
  asm volatile("st.global.v4.u32 [%0], {%1,%2,%3,%4};" ::"l"(p), "r"(v.x), "r"(v.y), "r"(v.z), "r"(v.w) : "memory");
}
__device__ __forceinline__ void wait_counter(const uint32_t* p, uint32_t target) {
  uint32_t n = 0;
  while (__any_sync(0xffffffffu, (int)(ld_acquire(p) - target) < 0)) { watchdog(n); }
}
__device__ __forceinline__ uint32_t tagf(float v, uint32_t tag) { return (__float_as_uint(v) & ~3u) | tag; }
__device__ __forceinline__ bool tag_ok(uint4 v, uint32_t tag) { return (((v.x ^ tag) | (v.y ^ tag) | (v.z ^ tag) | (v.w ^ tag)) & 3u) == 0; }
__device__ __forceinline__ float untag_sum(uint32_t a, uint32_t b) { return __uint_as_float(a & ~3u) + __uint_as_float(b & ~3u); }
__device__ __forceinline__ uint4 poll4(const uint32_t* p, uint32_t tag) {
  uint4 v = ld_relaxed4(p);
  uint32_t n = 0;
  while (!__all_sync(0xffffffffu, tag_ok(v, tag))) { v = ld_relaxed4(p); watchdog(n); }
  return v;
}
__device__ __forceinline__ float bf_lo(uint32_t v) { return __uint_as_float(v << 16); }
__device__ __forceinline__ float bf_hi(uint32_t v) { return __uint_as_float(v & 0xffff0000u); }
__device__ __forceinline__ uint32_t pack_bf(float lo, float hi) {
  uint32_t r; asm("cvt.rn.bf16x2.f32 %0, %1, %2;" : "=r"(r) : "f"(hi), "f"(lo)); return r;
}
__device__ __forceinline__ float rbf(float v) { return __uint_as_float(pack_bf(0.f, v) & 0xffff0000u); }
__device__ __forceinline__ uint32_t hmul2(uint32_t a, uint32_t b) {
  uint32_t r; asm("mul.rn.bf16x2 %0, %1, %2;" : "=r"(r) : "r"(a), "r"(b)); return r;
}
__device__ __forceinline__ uint32_t hadd2(uint32_t a, uint32_t b) {
  uint32_t r; asm("add.rn.bf16x2 %0, %1, %2;" : "=r"(r) : "r"(a), "r"(b)); return r;
}
__device__ __forceinline__ uint32_t hsub2(uint32_t a, uint32_t b) {
  uint32_t r; asm("sub.rn.bf16x2 %0, %1, %2;" : "=r"(r) : "r"(a), "r"(b)); return r;
}
__device__ __forceinline__ uint32_t hmax2(uint32_t a, uint32_t b) {
  uint32_t r; asm("max.bf16x2 %0, %1, %2;" : "=r"(r) : "r"(a), "r"(b)); return r;
}
__device__ __forceinline__ float rcp(float x) { float r; asm("rcp.approx.ftz.f32 %0, %1;" : "=f"(r) : "f"(x)); return r; }
__device__ __forceinline__ float ex2(float x) { float r; asm("ex2.approx.ftz.f32 %0, %1;" : "=f"(r) : "f"(x)); return r; }
__device__ __forceinline__ void stmatrix4(uint32_t addr, uint32_t a, uint32_t b, uint32_t c, uint32_t d) {
  asm volatile("stmatrix.sync.aligned.m8n8.x4.shared.b16 [%0], {%1,%2,%3,%4};" ::"r"(addr), "r"(a), "r"(b), "r"(c), "r"(d) : "memory");
}
__device__ __forceinline__ void ldmatrix4(uint32_t addr, uint32_t& a, uint32_t& b, uint32_t& c, uint32_t& d) {
  asm volatile("ldmatrix.sync.aligned.m8n8.x4.shared.b16 {%0,%1,%2,%3}, [%4];" : "=r"(a), "=r"(b), "=r"(c), "=r"(d) : "r"(addr) : "memory");
}
__device__ __forceinline__ void ldmatrix4t(uint32_t addr, uint32_t& a, uint32_t& b, uint32_t& c, uint32_t& d) {
  asm volatile("ldmatrix.sync.aligned.m8n8.x4.trans.shared.b16 {%0,%1,%2,%3}, [%4];" : "=r"(a), "=r"(b), "=r"(c), "=r"(d) : "r"(addr) : "memory");
}
__device__ __forceinline__ void mma16816(float (&d)[4], uint32_t a0, uint32_t a1, uint32_t a2, uint32_t a3, uint32_t b0, uint32_t b1) {
  asm volatile("mma.sync.aligned.m16n8k16.row.col.f32.bf16.bf16.f32 {%0,%1,%2,%3}, {%4,%5,%6,%7}, {%8,%9}, {%0,%1,%2,%3};"
               : "+f"(d[0]), "+f"(d[1]), "+f"(d[2]), "+f"(d[3]) : "r"(a0), "r"(a1), "r"(a2), "r"(a3), "r"(b0), "r"(b1));
}
__device__ __forceinline__ void sts1(uint32_t a, uint32_t v) { asm volatile("st.shared.u32 [%0], %1;" ::"r"(a), "r"(v) : "memory"); }
__device__ __forceinline__ uint4 lds4(uint32_t a) {
  uint4 v; asm volatile("ld.shared.v4.u32 {%0,%1,%2,%3}, [%4];" : "=r"(v.x), "=r"(v.y), "=r"(v.z), "=r"(v.w) : "r"(a) : "memory"); return v;
}
__device__ __forceinline__ uint2 lds2(uint32_t a) {
  uint2 v; asm volatile("ld.shared.v2.u32 {%0,%1}, [%2];" : "=r"(v.x), "=r"(v.y) : "r"(a) : "memory"); return v;
}
__device__ __forceinline__ uint32_t lds1(uint32_t a) {
  uint32_t v; asm volatile("ld.shared.u32 %0, [%1];" : "=r"(v) : "r"(a) : "memory"); return v;
}
__device__ __forceinline__ void sts2(uint32_t a, uint32_t x, uint32_t y) { asm volatile("st.shared.v2.u32 [%0], {%1,%2};" ::"r"(a), "r"(x), "r"(y) : "memory"); }
__device__ __forceinline__ void sts4(uint32_t a, uint4 v) {
  asm volatile("st.shared.v4.u32 [%0], {%1,%2,%3,%4};" ::"r"(a), "r"(v.x), "r"(v.y), "r"(v.z), "r"(v.w) : "memory");
}
__device__ __forceinline__ float silu_f(float v) { return __fdividef(v, 1.f + __expf(-v)); }
__device__ __forceinline__ uint32_t hfma2(uint32_t a, uint32_t b, uint32_t c) {
  uint32_t r; asm("fma.rn.bf16x2 %0, %1, %2, %3;" : "=r"(r) : "r"(a), "r"(b), "r"(c)); return r;
}
__device__ __forceinline__ void split_inv(float sd, uint32_t& ih, uint32_t& il) {
  const float inv = rcp(sd);
  ih = pack_bf(inv, inv);
  const float lo = inv - bf_lo(ih);
  il = pack_bf(lo, lo);
}
__device__ __forceinline__ uint32_t ln_norm(uint32_t x, uint32_t mean2, uint32_t ih, uint32_t il) {
  const uint32_t d = hsub2(x, mean2);
  return hfma2(d, ih, hmul2(d, il));
}
__device__ __forceinline__ uint32_t modul(uint32_t n, uint32_t c1, uint32_t sh) { return hadd2(hmul2(n, c1), sh); }
__device__ __forceinline__ uint32_t ln_mod(uint32_t x, uint32_t mean2, uint32_t ih, uint32_t il, uint32_t c1, uint32_t sh) {
  return modul(ln_norm(x, mean2, ih, il), c1, sh);
}

#define R8(a, i) "+f"(a[i]), "+f"(a[i + 1]), "+f"(a[i + 2]), "+f"(a[i + 3]), "+f"(a[i + 4]), "+f"(a[i + 5]), "+f"(a[i + 6]), "+f"(a[i + 7])
#define D64 "{%0,%1,%2,%3,%4,%5,%6,%7,%8,%9,%10,%11,%12,%13,%14,%15,%16,%17,%18,%19,%20,%21,%22,%23,%24,%25,%26,%27,%28,%29,%30,%31," \
            "%32,%33,%34,%35,%36,%37,%38,%39,%40,%41,%42,%43,%44,%45,%46,%47,%48,%49,%50,%51,%52,%53,%54,%55,%56,%57,%58,%59,%60,%61,%62,%63}"
template <int TB>
__device__ __forceinline__ void mma_ss(float (&d)[64], uint64_t da, uint64_t db, int sc) {
  asm volatile("{\n.reg .pred p;\nsetp.ne.b32 p, %66, 0;\n"
               "wgmma.mma_async.sync.aligned.m64n128k16.f32.bf16.bf16 " D64 ", %64, %65, p, 1, 1, 0, %67;\n}"
               : R8(d, 0), R8(d, 8), R8(d, 16), R8(d, 24), R8(d, 32), R8(d, 40), R8(d, 48), R8(d, 56)
               : "l"(da), "l"(db), "r"(sc), "n"(TB));
}
template <int TB>
__device__ __forceinline__ void mma_rs(float (&d)[64], uint32_t a0, uint32_t a1, uint32_t a2, uint32_t a3, uint64_t db, int sc) {
  asm volatile("{\n.reg .pred p;\nsetp.ne.b32 p, %69, 0;\n"
               "wgmma.mma_async.sync.aligned.m64n128k16.f32.bf16.bf16 " D64 ", {%64,%65,%66,%67}, %68, p, 1, 1, %70;\n}"
               : R8(d, 0), R8(d, 8), R8(d, 16), R8(d, 24), R8(d, 32), R8(d, 40), R8(d, 48), R8(d, 56)
               : "r"(a0), "r"(a1), "r"(a2), "r"(a3), "l"(db), "r"(sc), "n"(TB));
}
#define D128 "{%0,%1,%2,%3,%4,%5,%6,%7,%8,%9,%10,%11,%12,%13,%14,%15,%16,%17,%18,%19,%20,%21,%22,%23,%24,%25,%26,%27,%28,%29,%30,%31," \
             "%32,%33,%34,%35,%36,%37,%38,%39,%40,%41,%42,%43,%44,%45,%46,%47,%48,%49,%50,%51,%52,%53,%54,%55,%56,%57,%58,%59,%60,%61,%62,%63," \
             "%64,%65,%66,%67,%68,%69,%70,%71,%72,%73,%74,%75,%76,%77,%78,%79,%80,%81,%82,%83,%84,%85,%86,%87,%88,%89,%90,%91,%92,%93,%94,%95," \
             "%96,%97,%98,%99,%100,%101,%102,%103,%104,%105,%106,%107,%108,%109,%110,%111,%112,%113,%114,%115,%116,%117,%118,%119,%120,%121,%122,%123,%124,%125,%126,%127}"
#define R128(d, e) R8(d, 0), R8(d, 8), R8(d, 16), R8(d, 24), R8(d, 32), R8(d, 40), R8(d, 48), R8(d, 56), \
                   R8(e, 0), R8(e, 8), R8(e, 16), R8(e, 24), R8(e, 32), R8(e, 40), R8(e, 48), R8(e, 56)
__device__ __forceinline__ void mma256_ss(float (&d)[64], float (&e)[64], uint64_t da, uint64_t db, int sc) {
  asm volatile("{\n.reg .pred p;\nsetp.ne.b32 p, %130, 0;\n"
               "wgmma.mma_async.sync.aligned.m64n256k16.f32.bf16.bf16 " D128 ", %128, %129, p, 1, 1, 0, 1;\n}"
               : R128(d, e) : "l"(da), "l"(db), "r"(sc));
}
__device__ __forceinline__ void mma256_rs(float (&d)[64], float (&e)[64], uint32_t a0, uint32_t a1, uint32_t a2, uint32_t a3, uint64_t db) {
  asm volatile("{\n.reg .pred p;\nsetp.ne.b32 p, 1, 0;\n"
               "wgmma.mma_async.sync.aligned.m64n256k16.f32.bf16.bf16 " D128 ", {%128,%129,%130,%131}, %132, p, 1, 1, 1;\n}"
               : R128(d, e) : "r"(a0), "r"(a1), "r"(a2), "r"(a3), "l"(db));
}
template <int N> __device__ __forceinline__ void keep(float (&a)[N]) {
#pragma unroll
  for (int i = 0; i < N; i++) asm volatile("" : "+f"(a[i])::"memory");
}
template <int N> __device__ __forceinline__ void keep(uint32_t (&a)[N]) {
#pragma unroll
  for (int i = 0; i < N; i++) asm volatile("" : "+r"(a[i])::"memory");
}

#define STAMP(idx) do {} while (0)
#define PROF(grp, cond, idx) do {} while (0)

constexpr float SCL2 = 1.4426950408889634f * 0.08838834764831845f;

__device__ __forceinline__ void pack_p(const float (&s)[64], uint32_t (&p)[32]) {
#pragma unroll
  for (int i = 0; i < 32; i++) p[i] = pack_bf(s[2 * i], s[2 * i + 1]);
}

__device__ __forceinline__ void issue_qk(float (&s)[64], uint32_t q0, uint32_t q1, uint32_t kslot) {
  const uint64_t db = make_desc(kslot, 16, 1024), da0 = make_desc(q0, 16, 1024), da1 = make_desc(q1, 16, 1024);
#pragma unroll
  for (int kk = 0; kk < 8; kk++) mma_ss<0>(s, (kk < 4 ? da0 : da1) + (kk & 3) * 2, db + (kk >> 2) * 1024 + (kk & 3) * 2, kk != 0);
}
__device__ __forceinline__ void issue_pv(float (&o)[64], uint32_t (&p)[32], uint32_t vslot, int acc) {
  uint64_t db = make_desc(vslot, 16384, 1024);
#pragma unroll
  for (int kk = 0; kk < 8; kk++)
    mma_rs<1>(o, p[4 * kk], p[4 * kk + 1], p[4 * kk + 2], p[4 * kk + 3], db + kk * 128, kk == 0 ? acc : 1);
}

template <int H>
__device__ __forceinline__ void store_chunk(const float (&a)[64], uint32_t addr) {
#pragma unroll
  for (int i = 8 * H; i < 8 * H + 8; i += 2)
    stmatrix4(addr ^ ((i & 7) << 4), pack_bf(a[4 * i], a[4 * i + 1]), pack_bf(a[4 * i + 2], a[4 * i + 3]),
              pack_bf(a[4 * i + 4], a[4 * i + 5]), pack_bf(a[4 * i + 6], a[4 * i + 7]));
}
template <int H>
__device__ __forceinline__ void store_chunk(const float (&a)[64], float i0, float i1, uint32_t addr) {
#pragma unroll
  for (int i = 8 * H; i < 8 * H + 8; i += 2)
    stmatrix4(addr ^ ((i & 7) << 4), pack_bf(a[4 * i] * i0, a[4 * i + 1] * i0), pack_bf(a[4 * i + 2] * i1, a[4 * i + 3] * i1),
              pack_bf(a[4 * i + 4] * i0, a[4 * i + 5] * i0), pack_bf(a[4 * i + 6] * i1, a[4 * i + 7] * i1));
}
__device__ __forceinline__ float inv_quad_sum(float l) {
  l += __shfl_xor_sync(0xffffffffu, l, 1);
  l += __shfl_xor_sync(0xffffffffu, l, 2);
  return rcp(l);
}

__device__ __forceinline__ void write_table(uint32_t table, bool ca, uint32_t t, const uint4& m0, const uint4& m1) {
  float c0 = untag_sum(m0.x, m1.x), c1 = untag_sum(m0.y, m1.y), c2 = untag_sum(m0.z, m1.z), c3 = untag_sum(m0.w, m1.w);
  if (ca) { c0 = 1.f + rbf(c0); c1 = 1.f + rbf(c1); c2 = 1.f + rbf(c2); c3 = 1.f + rbf(c3); }
  const uint32_t d = table + (t >> 2) * 64 + (t & 1) * 32 + (t & 2) * 2 + (ca ? 0 : 8);
  sts1(d, pack_bf(c0, c1));
  sts1(d + 16, pack_bf(c2, c3));
}

__device__ __forceinline__ void ln_scalars(float mean, float var, float& mb, float& sd) {
  mb = rbf(mean);
  float r; asm("sqrt.approx.ftz.f32 %0, %1;" : "=f"(r) : "f"(rbf(rbf(var) + 1e-5f)));
  sd = rbf(r);
}

__global__ void __cluster_dims__(2, 1, 1) __launch_bounds__(384, 1) fused_kernel(const __grid_constant__ Maps maps, const Ptrs P) {
  extern __shared__ __align__(1024) uint8_t smem_raw[];
  const uint32_t base = smem_u32(smem_raw);
  const int tid = threadIdx.x, lane = tid & 31;
  const int warp = __shfl_sync(0xffffffffu, tid >> 5, 0);
  const int b = blockIdx.x;
  PROF(31, tid == 0, 0);

  if (b >= NMAIN) {
    float* sc = reinterpret_cast<float*>(smem_raw);
    float* red = sc + DM;
    for (int k = tid; k < DM; k += 384) sc[k] = rbf(silu_f(__bfloat162float(P.c[k])));
    __syncthreads();
    if (tid < 256) {
      const int col = 2048 + (b - NMAIN) * 1024 + (tid & 127) * 8, r0 = (tid >> 7) * 512;
      float acc[8];
#pragma unroll
      for (int e = 0; e < 8; e++) acc[e] = 0.f;
#pragma unroll 1
      for (int r = r0; r < r0 + 512; r += HU) {
        uint4 w[HU];
#pragma unroll
        for (int u = 0; u < HU; u++) w[u] = ldg_stream4(P.w_mod + (size_t)(r + u) * NMOD + col);
#pragma unroll
        for (int u = 0; u < HU; u++) {
          float s = sc[r + u];
          acc[0] += s * bf_lo(w[u].x); acc[1] += s * bf_hi(w[u].x); acc[2] += s * bf_lo(w[u].y); acc[3] += s * bf_hi(w[u].y);
          acc[4] += s * bf_lo(w[u].z); acc[5] += s * bf_hi(w[u].z); acc[6] += s * bf_lo(w[u].w); acc[7] += s * bf_hi(w[u].w);
        }
      }
      if (tid >= 128) {
#pragma unroll
        for (int e = 0; e < 8; e++) red[(tid & 127) * 8 + e] = acc[e];
      }
      const uint32_t tag = ld_relaxed(&g_epoch) % 3 + 1;
      bar_sync(1, 256);
      if (tid < 128) {
        uint32_t o[8];
#pragma unroll
        for (int e = 0; e < 8; e++) o[e] = __float_as_uint(rbf(acc[e] + red[tid * 8 + e])) | tag;
        st_relaxed4(g_mod + col, o[0], o[1], o[2], o[3]);
        st_relaxed4(g_mod + col + 4, o[4], o[5], o[6], o[7]);
        const uint4 wr = ldg_nc4(P.w_r + tid * 8);
        const uint32_t wv[4] = {wr.x, wr.y, wr.z, wr.w};
        float dsum = 0.f;
#pragma unroll
        for (int e = 0; e < 8; e++) {
          const float m = bf_hi(o[e]);
          dsum += (b == NMAIN + 2 ? rbf(1.f + m) : m) * ((e & 1) ? bf_hi(wv[e >> 1]) : bf_lo(wv[e >> 1]));
        }
#pragma unroll
        for (int k = 16; k > 0; k >>= 1) dsum += __shfl_xor_sync(0xffffffffu, dsum, k);
        if (lane == 0) st_relaxed(g_mod + (b - NMAIN) * 4 + warp, tagf(dsum, tag));
      }
    }
    PROF(2, tid == 0, 1);
    return;
  }

  const int rank = b & 1;
  const int rb = ((b >> 4) << 1) | rank, cj = (b >> 1) & 7;
  const bool late = b & 4;
  const uint32_t bfull = base + OFF_BAR, bempty = bfull + NSLOT * 8;
  const uint32_t gfull = bempty + NSLOT * 8, gempty = gfull + 32;
  const uint32_t bar_ofull = gempty + 32;
  const uint32_t bar_ofree = bar_ofull + 32;
  const uint32_t bar_par = bar_ofree + 32;
  const uint32_t bar_mod = bar_par + 8;
  const uint32_t bar_pread = bar_mod + 8;
  const uint32_t bar_xres = bar_pread + 8;
  const uint32_t bar_ring = bar_xres + 8;
  const uint32_t bar_box = bar_ring + 24;
  const uint32_t bar_go = bar_box + 96;
  const uint32_t bar_go2 = bar_go + 16;
  const uint32_t bar_cnt = bar_go + 24;
  const uint32_t xfull = bar_go + 40, xempty = xfull + 32;
  const uint32_t bar_hw = xempty + 32, bar_hx = bar_hw + 8;
  const uint32_t bar_hpub = bar_hx + 16;
  const uint32_t bar_win = bar_hpub + 16;
  const uint32_t bar_rx = bar_win + 8;
  const uint32_t bar_sel = bar_rx + 8;
  const uint32_t bar_gate = bar_sel + 8;
  const uint32_t bar_rel = bar_gate + 8;
  const uint32_t bar_od = bar_rel + 8;
  const uint32_t bar_mod2 = bar_od + 8;
  const uint32_t bar_res = bar_go + 8;
  const uint32_t stage = base + OFF_STAGE, par = base + OFF_PAR;

  if (warp == 10 && elect_one()) prefetch_map(&maps.wm);
  if (warp == 8 && elect_one()) {
    for (int s = 0; s < NSLOT; s++) { mbar_init(bfull + s * 8, 1); mbar_init(bempty + s * 8, 16); }
    for (int s = 0; s < 4; s++) { mbar_init(gfull + s * 8, 1); mbar_init(gempty + s * 8, 16); mbar_init(xfull + s * 8, 1); mbar_init(xempty + s * 8, 8); mbar_init(bar_ofree + s * 8, 1); mbar_init(bar_ofull + s * 8, 128); }
    mbar_init(bar_par, 64); mbar_init(bar_mod, 256); mbar_init(bar_pread, 2); mbar_init(bar_xres, 1);
    mbar_init(bar_ring, 8); mbar_init(bar_ring + 8, 8); mbar_init(bar_ring + 16, 8);
    mbar_init(bar_go, 1); mbar_init(bar_go2, 1); mbar_init(bar_cnt, 1); mbar_init(bar_cnt + 8, 1); mbar_init(bar_hpub, 8); mbar_init(bar_hpub + 8, 8); mbar_init(bar_res, 1); mbar_init(bar_win, 1); mbar_init(bar_rx, 1); mbar_init(bar_sel, 64); mbar_init(bar_gate, 8); mbar_init(bar_rel, 8); mbar_init(bar_od, 1); mbar_init(bar_mod2, 64);
    for (int s = 0; s < 12; s++) mbar_init(bar_box + s * 8, 1);
    asm volatile("fence.mbarrier_init.release.cluster;" ::: "memory");
    prefetch_map(&maps.x); prefetch_map(&maps.wq); prefetch_map(&maps.k); prefetch_map(&maps.v);
  }
  if (warp == 9 && elect_one()) {
    mbar_init(bar_hw, 1); mbar_init(bar_hx, 1); mbar_init(bar_hx + 8, 1);
    asm volatile("fence.mbarrier_init.release.cluster;" ::: "memory");
    mbar_expect_tx(bar_hw, 32768);
    mbar_expect_tx(bar_hx, 16384);
    mbar_expect_tx(bar_hx + 8, 16384);
    const __nv_bfloat16* xs = P.x + (size_t)(rb * 128 + cj * 16) * DM;
    bulk_load(base + 2 * GST_BYTES, xs, 16384, bar_hx);
    if (!late) {
      tma2d(stage, &maps.wm, (b >> 1) * 32, rank * 512, bar_hw);
      tma2d(stage + 16384, &maps.wm, (b >> 1) * 32, rank * 512 + 256, bar_hw);
    }
    bulk_load(base + 3 * GST_BYTES, xs + 8 * DM, 16384, bar_hx + 8);
  }
  cluster_arrive();

  if (warp >= 8) {
    asm volatile("setmaxnreg.dec.sync.aligned.u32 40;");
    if (warp < 10) bar_arrive(1, 320);
    const uint32_t epoch = ld_relaxed(&g_epoch);
    cluster_wait();
    if (warp == 8) {
      const int kvrow = (cj >> 1) * SK + (SK - WIN);
      int wch = cj * 8 + rank * 2;
#pragma unroll 1
      for (int ps = 0; ps < 3; ps++) {
        const CUtensorMap* mw = ps == 2 ? &maps.wo : &maps.wq;
        const uint32_t xt = ps == 1 ? XT1 : XT2, wt = ps == 0 ? WT0 : (ps == 1 ? WT1 : WT2);
        const int nst = ps == 2 ? 32 : 16;
#pragma unroll 1
        for (int i = 0; i < nst; i++) {
          const uint32_t bf = gfull + (i & 3) * 8;
          const int kt = ps == 2 ? (((cj & 1) * 4 + ((i >> 1) & 3)) * 4 + (i >> 3)) * 2 + (i & 1) : (ps ? i : slice_of(i) + (b & 14)) & 15;
          const uint32_t wd = base + unit_of(wt, i & 3) + rank * UNIT, xd = base + unit_of(xt, i & 3);
          const uint8_t* xs = g_act + (uint32_t)(rb * 80 + (ps - 1) * 16 + kt) * UNIT;
          if (ps == 0 && i == HD) mbar_wait(bar_mod, 0);
          const bool xfirst = ps && i < 2;
          if (ps == 2 && i == 0) mbar_wait(bar_ofree + 24, 0);
          if (i == 0) fence_async();
          mbar_wait(gempty + (i & 3) * 8, ((i >> 2) & 1) ^ 1);
          if (elect_one()) {
            mbar_expect_tx(bf, ps ? GST_BYTES : 2 * UNIT);
            if (xfirst) bulk_load_stream(xd, xs, UNIT, bf);
          }
          if (ps && i < 4) mbar_wait(bempty + i * 8, 1);
          if (elect_one()) tma3d_mc<true>(wd, mw, 0, (i == 31 ? kt ^ (rank * 32) : kt) * 64, i == 31 ? cj * 2 : wch, bf);
          if (ps) {
            if (i == 16 || i == 24) { mbar_wait(bar_cnt + i - 16, 0); fence_async(); }
            if (i == RES0) mbar_wait(bar_res, 0);
            if (i == 2) mbar_wait(bar_ofree + (ps - 1) * 16, 0);
            if (elect_one()) {
              if (i == 31) bulk_load(xd, xs, UNIT, bf); else if (!xfirst) bulk_load_stream(xd, xs, UNIT, bf);
              mbar_arrive_pred(bar_go, i == GOST - 1);
              if (PG0 < 16) mbar_arrive_pred(bar_go2, ps == 1 && i == PG0);
              mbar_arrive_pred(bar_od, i == (ps == 1 ? ODS1 : ODS));
              if (i == RES0) mbar_expect_tx(bar_xres, 32768);
              if (i == RES0 || i == RES1) tma2d(base + OFF_RES + (i == RES1) * UNIT, &maps.x, cj * 128 + (i == RES1) * 64, rb * 128, bar_xres);
            }
          }
        }
        if (ps == 2) break;
        wch = ps ? ((wch >> 3) ^ rank) * 2 : wch + 4;
#pragma unroll 1
        for (int u = 0; u < 16; u++) {
          const bool isk = (u == 0) || ((u & 1) && u < 15);
          const int blk = (isk ? (u + 1) >> 1 : (u == 15 ? 7 : (u >> 1) - 1)) & 3;
          const uint32_t sl = base + unit_of(ps ? AT1 : AT0, u & 3) + rank * UNIT, bf = bfull + (u & 3) * 8;
          if (u < 4) mbar_wait(gempty + ((u + 1) >> 1) * 8, 1);
          mbar_wait(bempty + (u & 3) * 8, ((u >> 2) & 1) ^ 1);
          if (elect_one()) {
            mbar_arrive_pred(bar_go2, ps && u + 16 == PG0);
            mbar_expect_tx(bf, SLOT_BYTES);
            tma3d_mc<false>(sl, isk ? &maps.k : &maps.v, 0, kvrow + blk * 128, rank, bf);
          }
        }
      }
      if (elect_one()) mbar_expect_tx(bar_rx, UNIT);
      mbar_wait(bar_rel, 0);
      if (elect_one()) {
        bulk_load_stream(base + UNIT, g_act + (uint32_t)(rb * 80 + 16 + 63 - (cj & 1) * 32) * UNIT, UNIT, bar_rx);
      }
      if (b < NFFN) {
#pragma unroll 1
        for (int u = 0; u < 12; u++) {
          const uint32_t dst = base + unit_of(u < 4 ? FT_G : (u < 8 ? FT_U : FT_D), u & 3);
          if (elect_one()) mbar_expect_tx(bar_box + u * 8, UNIT);
          if (u == FB0 || u == FB1 || u == FB2) mbar_wait(bar_ring + (u == FB2 ? 16 : u == FB1 ? 8 : 0), 0);
          const int fp = u < FPB ? FPACE0 : FPACE;
          if (u >= fp) mbar_wait(bar_box + (u - fp) * 8, 0);
          if (elect_one()) {
            if (u < 8) tma2d(dst, u < 4 ? &maps.wg : &maps.wu, b * 32, (u & 3) * 256, bar_box + u * 8);
            else tma3d(dst, &maps.wd, 0, b * 32, (u - 8) * 4, bar_box + u * 8);
          }
        }
      }
    } else if (warp == 9) {
      const uint32_t target = 8 * (epoch + 1);
      uint32_t hmask = 0;
#pragma unroll 1
      for (int i = 0; i < 16; i++) {
        if (i == HDX) mbar_wait(bar_mod, 0);
        const int kt = (2 * cj + slice_of(i)) & 15;
        const uint32_t need = i == 15 ? 0xffffu : 1u << kt;
        if (i >= NRS && (hmask & need) != need) {
          uint32_t n = 0;
          do { hmask = __ballot_sync(0xffffffffu, ld_acquire(&g_cnt_h[rb * 32 + (lane & 15)]) == epoch + 1); watchdog(n); } while ((hmask & need) != need);
          PROF(1, lane == 0 && i == NRS, 26);
          fence_async();
        }
        mbar_wait(xempty + (i & 3) * 8, ((i >> 2) & 1) ^ 1);
        if (elect_one()) {
          mbar_expect_tx(xfull + (i & 3) * 8, UNIT);
          if (i < NRS) tma2d(base + (i & 3) * GST_BYTES, &maps.x, kt * 64, rb * 128, xfull + (i & 3) * 8);
          else bulk_load_stream(base + (i & 3) * GST_BYTES, g_act + (uint32_t)(rb * 80 + kt) * UNIT, UNIT, xfull + (i & 3) * 8);
        }
      }
      prefetch_map(&maps.wo);
#pragma unroll 1
      for (int t = 0; t < 4; t++) {
        if (t & 1) mbar_wait(bar_od, t >> 1);
#pragma unroll 1
        for (int p = 0; p < 32768 / OPS; p++) {
          const uint32_t w = p / (16384 / OPS), c = (p / (8192 / OPS)) & 1, off = w * 8192 + (p % (8192 / OPS)) * OPS;
          mbar_wait(bar_ofull + (t & 1) * 16 + w * 8, t >> 1);
          if (elect_one()) {
            bulk_store(g_act + (uint32_t)(rb * 80 + 16 + (cj * 4 + t) * 2 + c) * UNIT + off, base + unit_of(QT, 2 * t + c) + off, OPS);
            asm volatile("cp.async.bulk.commit_group;" ::: "memory");
            asm volatile("cp.async.bulk.wait_group.read %0;" ::"n"(OFL) : "memory");
          }
        }
        if (elect_one()) {
          asm volatile("cp.async.bulk.wait_group.read 0;" ::: "memory");
          mbar_arrive(t < 3 ? bar_ofree + t * 8 : bar_res);
          asm volatile("cp.async.bulk.wait_group 0;" ::: "memory");
          fence_async();
          red_release(&g_cnt_o[((rb * 4 + t) * 2 + (cj >> 2)) * 32], 2);
        }
        if (t) {
          wait_counter(&g_cnt_o[(rb * 8 + 2 * t + (cj & 1)) * 32], target);
          if (t & 1) wait_counter(&g_cnt_o[(rb * 8 + (t == 1 ? cj & 1 : 7 - (cj & 1))) * 32], target);
          if (elect_one()) mbar_arrive(t == 1 ? bar_ofree + 24 : bar_cnt + t * 8 - 16);
        }
      }
      PROF(2, lane == 0, 27);
      const uint32_t tag = epoch % 3 + 1;
      const uint32_t* inbox = g_cand + (lane & 15);
      mbar_wait(bar_ring + 16, 0);
      uint32_t c0 = ld_relaxed(inbox), n = 0;
#define CAND_STEP(cv)                                                                                        \
      {                                                                                                      \
        const bool valid = (cv & 3u) == tag, all = __all_sync(0xffffffffu, valid);                           \
        const uint32_t best = __reduce_max_sync(0xffffffffu, valid ? cv : 0u);                               \
        const uint32_t blk = __ffs(__ballot_sync(0xffffffffu, cv == best)) - 1;                              \
        if (best) sts2(par + PAR_CONST + 56, best, (blk << 7 | (~best >> 2 & 127)) | (all ? 0x1800 : 0x800)); \
        if (all) break;                                                                                      \
        cv = ld_relaxed(inbox);                                                                              \
      }
      while (true) { CAND_STEP(c0) watchdog(n); }
    } else {
      const int t2 = tid - 320;
      if (late && warp == 10) {
        mbar_wait(bar_hx, 0);
        if (elect_one()) {
          tma2d(stage, &maps.wm, (b >> 1) * 32, rank * 512, bar_hw);
          tma2d(stage + 16384, &maps.wm, (b >> 1) * 32, rank * 512 + 256, bar_hw);
        }
      }
      {
        const uint32_t tag = epoch % 3 + 1;
        mbar_wait(bar_hx + 8, 0);
        mbar_wait(bar_hw, 0);
        __nanosleep(late ? OSL2 : OSL);
        {
          const uint32_t t7 = (warp & 1) * 64 + (lane >> 4) * 32 + 16 + (lane & 15);
          const uint32_t* pm = g_modp + ((cj * 128 + t7 * 4) & (DM - 1));
          uint4 m0, m1, m2, m3;
          uint32_t n = 0;
          do {
            m0 = ld_relaxed4(pm); m1 = ld_relaxed4(pm + 2 * DM); m2 = ld_relaxed4(pm + DM); m3 = ld_relaxed4(pm + 3 * DM);
            watchdog(n);
          } while (!__all_sync(0xffffffffu, tag_ok(m0, tag) && tag_ok(m1, tag) && tag_ok(m2, tag) && tag_ok(m3, tag)));
          write_table(par, false, t7, m0, m1);
          write_table(par, true, t7, m2, m3);
          mbar_arrive(bar_mod2);
        }
      }
      mbar_wait(bar_hpub + (warp & 1) * 8, 0);
      PROF(1, t2 == 0, 24);
#pragma unroll 1
      for (int c = 0; c < 8; c++) {
        const uint32_t off = (warp & 1) * UNIT + c * 2048 + lane * 16;
        uint8_t* dst = g_act + (uint32_t)(rb * 80 + cj * 2) * UNIT + off;
        const uint4 v0 = lds4(stage + off), v1 = lds4(stage + off + 512), v2 = lds4(stage + off + 1024), v3 = lds4(stage + off + 1536);
        stg4(dst, v0); stg4(dst + 512, v1); stg4(dst + 1024, v2); stg4(dst + 1536, v3);
      }
      __syncwarp();
      PROF(1, t2 == 0, 15);
      if (lane == 0) {
        mbar_arrive(bar_pread);
        red_release(&g_cnt_h[rb * 32 + cj * 2 + (warp & 1)], 1);
        PROF(1, t2 == 0, 25);
        prefetch_map(&maps.wg); prefetch_map(&maps.wu); prefetch_map(&maps.wd); prefetch_map(&maps.out);
      }
      __syncwarp();
      if (b < NFFN) {
        mbar_wait(bar_go2, 0);
        const __nv_bfloat16* pg = ((b & 1) ? P.w_up : P.w_gate) + (b >> 1) * 64 + (size_t)t2 * FF;
        const __nv_bfloat16* pd = P.w_down + (size_t)b * 32768 + t2 * 64;
        PROF(2, t2 == 0, 13);
#pragma unroll 1
        for (int i = 0; i < WN; i += WB) {
          uint32_t v[WB];
#pragma unroll
          for (int u = 0; u < WB; u++) {
            const int k = i + u;
            asm volatile("ld.global.cg.L2::128B.u32 %0, [%1];" : "=r"(v[u]) : "l"(k < 16 ? pg + (size_t)k * 64 * FF : pd + (k - 16) * 4096));
          }
#pragma unroll
          for (int u = 1; u < WB; u++) v[0] ^= v[u];
          sts1(par + PAR_SINK + t2 * 4, v[0]);
        }
        PROF(2, t2 == 0, 14);
      }
      const uint32_t tag = epoch % 3 + 1;
      mbar_wait(bar_go, 0);
      bar_sync(4, 64);
      if (warp == 10) {
        const uint32_t* src = g_mod + 2 * DM + cj * 128 + lane * 4;
        const uint2 wr = *reinterpret_cast<const uint2*>(P.w_r + cj * 128 + lane * 4);
        uint4 vga, vsb, vcb, vgb;
        uint32_t n = 0;
        do {
          vga = ld_relaxed4(src); vsb = ld_relaxed4(src + DM); vcb = ld_relaxed4(src + 2 * DM); vgb = ld_relaxed4(src + 3 * DM);
          watchdog(n);
        } while (!__all_sync(0xffffffffu, tag_ok(vga, tag) && tag_ok(vsb, tag) && tag_ok(vcb, tag) && tag_ok(vgb, tag)));
        const float c0 = rbf(1.f + bf_hi(vcb.x)), c1 = rbf(1.f + bf_hi(vcb.y)), c2 = rbf(1.f + bf_hi(vcb.z)), c3 = rbf(1.f + bf_hi(vcb.w));
        const float a0 = c0 * bf_lo(wr.x), a1 = c1 * bf_hi(wr.x), a2 = c2 * bf_lo(wr.y), a3 = c3 * bf_hi(wr.y);
        const uint32_t h0 = pack_bf(a0, a1), h1 = pack_bf(a2, a3);
        const uint32_t t1 = par + PAR_T1 + (lane >> 2) * 64 + (lane & 1) * 32 + (lane & 2) * 2;
        sts1(t1, h0); sts1(t1 + 8, pack_bf(a0 - bf_lo(h0), a1 - bf_hi(h0)));
        sts1(t1 + 16, h1); sts1(t1 + 24, pack_bf(a2 - bf_lo(h1), a3 - bf_hi(h1)));
        const uint32_t tg = par + PAR_SINK + (lane >> 3) * 64 + (lane & 1) * 32 + (lane & 6) * 2;
        sts1(tg, __byte_perm(vga.x, vga.y, 0x7632)); sts1(tg + 16, __byte_perm(vga.z, vga.w, 0x7632));
        sts4(par + PAR_T2 + lane * 32, make_uint4(pack_bf(c0, c1), __byte_perm(vsb.x, vsb.y, 0x7632), __byte_perm(vgb.x, vgb.y, 0x7632), __byte_perm(vga.x, vga.y, 0x7632)));
        sts4(par + PAR_T2 + lane * 32 + 16, make_uint4(pack_bf(c2, c3), __byte_perm(vsb.z, vsb.w, 0x7632), __byte_perm(vgb.z, vgb.w, 0x7632), __byte_perm(vga.z, vga.w, 0x7632)));
      } else {
        const uint4 g = poll4((lane & 2) ? g_mod + 8 - (lane & 1) * 4 : g_mod + 5 * DM + b * 8 + (lane & 1) * 4, tag);
        sts1(par + PAR_CONST + 60, 0);
        if (lane < 2) sts4(par + PAR_CONST + 16 + lane * 16, g);
        else if (lane < 4) sts2(par + PAR_CONST + (lane - 2) * 8, __float_as_uint(untag_sum(g.x, g.y) + untag_sum(g.z, g.w)), epoch);
      }
      __syncwarp();
#pragma unroll 4
      for (int q = 0; q < 32; q++) st_b128(g_xch + ((size_t)b * 8 * 256 + q * 64 + t2) * 4, (epoch & 1) << 16, 0, 0, 0);
      for (int q = 0; q < 2; q++) st_relaxed4(g_stats + ((size_t)cj * SEQ + rb * 128 + q * 64 + t2) * 4, 0, 0, 0, 0);
      if (b < NFFN)
        for (int q = 0; q < 4; q++) st_relaxed4(g_ypart + ((size_t)(q * 32 + (t2 >> 1)) * NFFN + b) * 8 + (t2 & 1) * 4, 0, 0, 0, 0);
      st_relaxed4(g_row + rb * 2 * DM + (t2 >> 5) * DM + cj * 128 + (t2 & 31) * 4, 0, 0, 0, 0);
      __threadfence();
      mbar_arrive(bar_par);
      mbar_wait(bar_gate, 0);
      uint32_t have = 0, n = 0;
      while (true) {
        const uint32_t st = lds1(par + PAR_CONST + 60) >> 7;
        if ((st & 31) != have) {
          const uint32_t* hsrc = g_row + (st & 15) * 2 * DM + t2 * 4;
          uint4 hv[4];
          bool ok = true;
#pragma unroll
          for (int i = 0; i < 4; i++) hv[i] = ld_pairs(hsrc + i * 256);
#pragma unroll
          for (int i = 0; i < 4; i++) {
            sts2(base + ((FT_G >> i * 4) & 15) * UNIT + (warp & 1) * 8192 + 256 + lane * 8, hv[i].x, hv[i].z);
            ok = ok && hv[i].y == tag && hv[i].w == tag;
          }
          have = __all_sync(0xffffffffu, ok) ? st & 31 : 0;
        }
        if ((st ^ have) == 32) break;
        watchdog(n);
      }
      mbar_arrive(bar_sel);
    }
    __syncwarp();
    cluster_arrive();
    {
      const uint32_t tag = epoch % 3 + 1, t3 = tid - 256;
      mbar_wait(bar_win, 0);
      uint2 win = lds2(par + PAR_CONST + 56);
      win.y &= 0x7ff;
      const uint32_t* fsrc = g_row + (win.y >> 7) * 2 * DM + (b >> 1) * 16 + (t3 & 3) * 4 + (b & 1) * 2;
      const uint32_t* ysrc = g_ypart + (size_t)b * NFFN * 8 + min(t3, NFFN - 1) * 4;
      uint2 fh = ld_pair(fsrc), fx = ld_pair(fsrc + DM);
      if (PSL) __nanosleep(PSL);
      uint4 ya = ld_relaxed4(ysrc), yb = ld_relaxed4(ysrc + NFFN * 4);
      const float rwin = __uint_as_float(((int)win.x < 0 ? win.x & 0x7fffffffu : ~win.x) & ~0x1ffu);
      const float rs = rbf(rcp(1.f + __expf(-rbf(rwin))));
      uint32_t n = 0;
      while (__any_sync(0xffffffffu, fh.y != tag || fx.y != tag)) { fh = ld_pair(fsrc); fx = ld_pair(fsrc + DM); watchdog(n); }
      while (!__all_sync(0xffffffffu, tag_ok(ya, tag) && tag_ok(yb, tag))) {
        if (!tag_ok(ya, tag)) ya = ld_relaxed4(ysrc);
        if (!tag_ok(yb, tag)) yb = ld_relaxed4(ysrc + NFFN * 4);
        watchdog(n);
      }
      __syncwarp();
      PROF(8, t3 == 0, 5);
      float y0 = untag_sum(ya.x, yb.x), y1 = untag_sum(ya.y, yb.y), y2 = untag_sum(ya.z, yb.z), y3 = untag_sum(ya.w, yb.w);
      const bool u1 = lane & 2, u2 = lane & 4;
      y0 = (u1 ? y2 : y0) + __shfl_xor_sync(0xffffffffu, u1 ? y0 : y2, 2);
      y1 = (u1 ? y3 : y1) + __shfl_xor_sync(0xffffffffu, u1 ? y1 : y3, 2);
      y0 = (u2 ? y1 : y0) + __shfl_xor_sync(0xffffffffu, u2 ? y0 : y1, 4);
      y0 += __shfl_xor_sync(0xffffffffu, y0, 8);
      if (!(lane & 8)) sts1(par + PAR_RED + 64 + (t3 >> 4) * 32 + ((lane & 1) * 4 + (lane & 2) + ((lane >> 2) & 1)) * 4, __float_as_uint(y0));
      bar_sync(4, 128);
      if (t3 < 4) {
        y0 = 0.f; y1 = 0.f;
#pragma unroll
        for (int w4 = 0; w4 < 7; w4++) {
          const uint2 v = lds2(par + PAR_RED + 64 + w4 * 32 + t3 * 8);
          y0 += __uint_as_float(v.x); y1 += __uint_as_float(v.y);
        }
        const uint2 gv = lds2(par + PAR_CONST + 16 + t3 * 8);
        const uint32_t upd = hmul2(pack_bf(y0, y1), pack_bf(rs, rs));
        *reinterpret_cast<uint32_t*>(P.out + (size_t)win.y * DM + b * 8 + t3 * 2) =
            hadd2(fx.x, hmul2(__byte_perm(gv.x, gv.y, 0x7632), hadd2(fh.x, upd)));
        if (b == 0 && t3 == 0) st_relaxed(&g_epoch, epoch + 1);
      }
      PROF(31, t3 == 0, 36);
    }
    cluster_wait();
  } else {
    const int wg = warp >> 2;

    uint32_t tag;
    {
      uint32_t* const pmod = g_modp + rank * 2 * DM + (b >> 1) * 32 + lane;
      uint32_t* const pln = g_ln1 + (rb * 128 + cj * 16 + warp) * 4;
      uint32_t sc[8];
#pragma unroll
      for (int k = 0; k < 8; k++) sc[k] = ldg_nc1(P.c + rank * 512 + warp * 64 + k * 8 + (lane & 3) * 2);
      const uint32_t epoch = ld_relaxed(&g_epoch);
      if (warp == 0) st_relaxed(pmod, 0);
      if (lane == 0) { st_b128(pln, 0, 0, 0, 0); st_b128(pln + 32, 0, 0, 0, 0); }
      asm volatile("setmaxnreg.inc.sync.aligned.u32 232;");
      bar_sync(1, 320);
#pragma unroll
      for (int k = 0; k < 8; k++) sc[k] = pack_bf(silu_f(bf_lo(sc[k])), silu_f(bf_hi(sc[k])));
      keep(sc);
      tag = epoch % 3 + 1;
#pragma unroll
      for (int part = 0; part < 4; part++) {
        if (!(part & 1)) {
          const uint32_t xa = base + (2 + part / 2) * GST_BYTES + warp * 2048 + lane * 16;
          mbar_wait(bar_hx + part * 4, 0);
          float s0 = 0.f, s1 = 0.f, q0 = 0.f, q1 = 0.f;
#pragma unroll
          for (int q = 0; q < 4; q++) {
            const uint4 xv = lds4(xa + q * 512);
            const uint32_t u[4] = {xv.x, xv.y, xv.z, xv.w};
#pragma unroll
            for (int e = 0; e < 4; e++) { const float lo = bf_lo(u[e]), hi = bf_hi(u[e]); s0 += lo; s1 += hi; q0 += lo * lo; q1 += hi * hi; }
          }
          s0 += s1; q0 += q1;
#pragma unroll
          for (int o = 16; o > 0; o >>= 1) { s0 += __shfl_xor_sync(0xffffffffu, s0, o); q0 += __shfl_xor_sync(0xffffffffu, q0, o); }
          const float mean = s0 * (1.f / DM);
          float mb, sd;
          ln_scalars(mean, fmaxf(q0 * (1.f / DM) - mean * mean, 0.f), mb, sd);
          uint32_t ih, il;
          split_inv(sd, ih, il);
          if (lane == 0) st_b128(pln + part * 16, pack_bf(mb, mb), ih, il, tag);
          PROF(1, tid == 0 && part == 2, 4);
        } else if (late == (part == 3)) {
          const uint32_t fr = (lane & 7) + (lane >> 4) * 8, tq = lane & 3;
          const uint32_t wa = stage + warp * 4096 + fr * 64 + ((((lane >> 3) & 1) ^ ((fr >> 1) & 3)) << 4);
          float d0[4] = {0.f, 0.f, 0.f, 0.f}, d1[4] = {0.f, 0.f, 0.f, 0.f};
          mbar_wait(bar_hw, 0);
#pragma unroll
          for (int ks = 0; ks < 4; ks++) {
            uint32_t w[8];
            ldmatrix4t(wa + ks * 1024, w[0], w[1], w[2], w[3]);
            ldmatrix4t((wa ^ 32) + ks * 1024, w[4], w[5], w[6], w[7]);
            mma16816(d0, w[0], w[1], w[2], w[3], sc[2 * ks], sc[2 * ks + 1]);
            mma16816(d1, w[4], w[5], w[6], w[7], sc[2 * ks], sc[2 * ks + 1]);
          }
          sts1(base + 2 * GST_BYTES + warp * 2048 + (tq * 8 + (lane >> 2)) * 4, __float_as_uint((tq & 2) ? ((tq & 1) ? d1[2] : d1[0]) : ((tq & 1) ? d0[2] : d0[0])));
          bar_sync(1, 256);
          if (warp == 0) {
            float s = 0.f;
#pragma unroll
            for (int w8 = 0; w8 < 8; w8++) s += __uint_as_float(lds1(base + 2 * GST_BYTES + w8 * 2048 + lane * 4));
            st_relaxed(pmod, (__float_as_uint(s) & ~3u) | tag);
          }
          PROF(1, tid == 0, 3);
        }
      }
      cluster_wait();
      if (wg == 1) bar_arrive(2, 256);
    }

    float f0 = 0.f, f1 = 0.f;
    const uint32_t rempty = lane < 2 ? mapa(bempty, lane & 1) : 0;
    constexpr uint32_t GE = NSLOT * 8 + 32;
    float o[64], s[64];
#pragma unroll 1
    for (int ps = 0; ps < 3; ps++) {
      {
        const uint32_t xt = ps == 1 ? XT1 : XT2, wt = ps == 1 ? WT1 : WT2;
        const int nst = ps == 2 ? 28 : 14;
        if (ps == 0) {
          float ga[64], gb[64];
#pragma unroll
          for (int i = 0; i < 64; i++) { ga[i] = 0.f; gb[i] = 0.f; }
          uint32_t a[2][16];
          const uint32_t l = fresh_lane();
          uint32_t fa[4];
#pragma unroll
          for (int kk = 0; kk < 4; kk++) fa[kk] = (base + wg * 8192 + frag_offset(warp)) ^ (kk * 32);
          const uint32_t mt = par + (l & 3) * 16;
          auto fetch = [&](int i, uint32_t (&f)[16], uint32_t z) {
            mbar_wait(xfull + (i & 3) * 8, i >> 2);
#pragma unroll
            for (int kk = 0; kk < 4; kk++) ldmatrix4(fa[kk] + (i & 3) * GST_BYTES + z, f[4 * kk], f[4 * kk + 1], f[4 * kk + 2], f[4 * kk + 3]);
          };
          const bool oddw = warp & 2;
          uint4 r0, r1;
          {
            const uint32_t t7 = (warp & 1) * 64 + (l >> 4) * 32 + (l & 15);
            const uint32_t* pm = g_modp + wg * DM + ((cj * 128 + t7 * 4) & (DM - 1));
            const uint32_t* pr = g_ln1 + (rb * 128 + warp * 16 + (l >> 2)) * 4;
            uint4 m0 = make_uint4(tag, tag, tag, tag), m1 = m0;
            if (!oddw) { m0 = ld_relaxed4(pm); m1 = ld_relaxed4(pm + 2 * DM); }
            r0 = ld_b128(pr); r1 = ld_b128(pr + 32);
            fetch(0, a[0], 0); fetch(1, a[1], 0);
            uint32_t n = 0;
            bool written = false;
#pragma unroll 1
            while (true) {
              uint32_t miss;
              asm volatile("{ .reg .pred p0, p1, p2, p3; .reg .b32 t, u;\n"
                           "lop3.b32 t, %1, %2, %19, 0x7e; lop3.b32 u, %3, %4, %19, 0x7e; or.b32 t, t, u; and.b32 t, t, 3; setp.ne.u32 p0, t, 0;\n"
                           "lop3.b32 t, %5, %6, %19, 0x7e; lop3.b32 u, %7, %8, %19, 0x7e; or.b32 t, t, u; and.b32 t, t, 3; setp.ne.u32 p1, t, 0;\n"
                           "setp.ne.u32 p2, %12, %19; setp.ne.u32 p3, %16, %19;\n"
                           "@p0 ld.relaxed.gpu.global.v4.u32 {%1, %2, %3, %4}, [%17];\n"
                           "@p1 ld.relaxed.gpu.global.v4.u32 {%5, %6, %7, %8}, [%17 + 8192];\n"
                           "@p2 ld.relaxed.gpu.global.v4.u32 {%9, %10, %11, %12}, [%18];\n"
                           "@p3 ld.relaxed.gpu.global.v4.u32 {%13, %14, %15, %16}, [%18 + 128];\n"
                           "or.pred p0, p0, p1; or.pred p2, p2, p3; vote.sync.any.pred p0, p0, 0xffffffff; vote.sync.any.pred p2, p2, 0xffffffff;\n"
                           "selp.u32 t, 1, 0, p0; selp.u32 u, 2, 0, p2; or.b32 %0, t, u; }"
                           : "=r"(miss), "+r"(m0.x), "+r"(m0.y), "+r"(m0.z), "+r"(m0.w), "+r"(m1.x), "+r"(m1.y), "+r"(m1.z), "+r"(m1.w),
                             "+r"(r0.x), "+r"(r0.y), "+r"(r0.z), "+r"(r0.w), "+r"(r1.x), "+r"(r1.y), "+r"(r1.z), "+r"(r1.w)
                           : "l"(pm), "l"(pr), "r"(tag) : "memory");
              if (!(miss & 1) && !written) {
                written = true;
                if (!oddw) write_table(par, wg, t7, m0, m1);
                mbar_arrive(bar_mod);
              }
              if (!miss) break;
              watchdog(n);
            }
          }
          const uint32_t zero = r0.w ^ tag;
          auto normalize = [&](uint32_t (&f)[16]) {
#pragma unroll
            for (int k = 0; k < 16; k += 2) { f[k] = ln_norm(f[k], r0.x, r0.y, r0.z); f[k + 1] = ln_norm(f[k + 1], r1.x, r1.y, r1.z); }
          };
          auto modulate = [&](int i, uint32_t (&f)[16]) {
#pragma unroll
            for (int kk = 0; kk < 4; kk++) {
              const uint4 m = lds4(mt + slice_of(i) * 256 + kk * 64);
              f[4 * kk] = MODUL(f[4 * kk], m.x, m.z); f[4 * kk + 1] = MODUL(f[4 * kk + 1], m.x, m.z);
              f[4 * kk + 2] = MODUL(f[4 * kk + 2], m.y, m.w); f[4 * kk + 3] = MODUL(f[4 * kk + 3], m.y, m.w);
            }
            keep(f);
            mbar_arrive_pred(xempty + (i & 3) * 8, l == 0);
          };
          auto publish = [&](int u, uint32_t (&f)[16]) {
#pragma unroll
            for (int kk = 0; kk < 4; kk++) stmatrix4(fa[kk] + OFF_STAGE + u * UNIT, f[4 * kk], f[4 * kk + 1], f[4 * kk + 2], f[4 * kk + 3]);
            __syncwarp();
            mbar_arrive_pred(bar_hpub + u * 8, l == 0);
          };
          auto multiply = [&](int i, uint32_t (&f)[16]) {
            mbar_wait(gfull + (i & 3) * 8, i >> 2);
            const uint64_t db = make_desc(base + (i & 3) * GST_BYTES + UNIT, 8192, 1024);
            wg_fence();
#pragma unroll
            for (int kk = 0; kk < 4; kk++) mma256_rs(ga, gb, f[4 * kk], f[4 * kk + 1], f[4 * kk + 2], f[4 * kk + 3], db + kk * 128);
            wg_commit();
          };
          auto next = [&](int i, uint32_t (&f)[16]) {
            wg_wait<1>();
            mbar_arrive_cl(rempty, GE + ((i + 2) & 3) * 8);
            uint32_t z = zero;
#pragma unroll
            for (int k = 0; k < 16; k += 2) asm volatile("lop3.b32 %0, %1, %2, %0, 0xA8;" : "+r"(z) : "r"(f[k]), "r"(f[k + 1]));
            fetch(i, f, z);
            normalize(f);
            if (i == 2) { keep(f); mbar_wait(bar_mod2, 0); }
            modulate(i, f); multiply(i, f);
          };
          normalize(a[0]); normalize(a[1]);
          keep(a[0]); keep(a[1]);
          mbar_wait(bar_mod, 0);
          PROF(1, tid == 0, 2);
          modulate(0, a[0]); multiply(0, a[0]); publish(0, a[0]);
          modulate(1, a[1]); multiply(1, a[1]);
#pragma unroll 1
          for (int i = 2; i < NRS; i += 2) {
            next(i, a[0]);
            if (i == 2) publish(1, a[0]);
            next(i + 1, a[1]);
          }
          wg_wait<1>();
          mbar_arrive_cl(rempty, GE + ((NRS + 2) & 3) * 8);
#pragma unroll 1
          for (int i = NRS; i < 14; i++) {
            mbar_wait(xfull + (i & 3) * 8, (i >> 2) & 1);
            mbar_wait(gfull + (i & 3) * 8, (i >> 2) & 1);
            const uint32_t xa = base + (i & 3) * GST_BYTES;
            const uint64_t da = make_desc(xa + wg * 8192, 16, 1024), db = make_desc(xa + UNIT, 8192, 1024);
            if (i == 13) bar_sync(2 + wg, 256);
            wg_fence();
#pragma unroll
            for (int kk = 0; kk < 4; kk++) mma256_ss(ga, gb, da + kk * 2, db + kk * 128, 1);
            wg_commit();
            if (i == 13) bar_arrive(3 - wg, 256);
            wg_wait<1>();
            uint32_t z = zero;
#pragma unroll
            for (int k = 0; k < 16; k += 2) asm volatile("lop3.b32 %0, %1, %2, %0, 0xA8;" : "+r"(z) : "r"(a[1][k]), "r"(a[1][k + 1]));
            mbar_arrive_cl(rempty, GE + ((i + 3) & 3) * 8 + z);
            mbar_arrive_pred(xempty + ((i + 3) & 3) * 8, l == 0 && i != NRS);
          }
          mbar_wait(xfull + 16, 1);
          wg_wait<0>();
          keep(ga); keep(gb);
#pragma unroll
          for (int i = 0; i < 64; i++) {
            asm volatile("mov.b32 %0, %1;" : "=f"(s[i]) : "f"(ga[i]));
            asm volatile("mov.b32 %0, %1;" : "=f"(o[i]) : "f"(gb[i]));
          }
        } else {
          float ga[64], gb[64];
#pragma unroll
          for (int i = 0; i < 64; i++) {
            asm volatile("mov.b32 %0, %1;" : "=f"(ga[i]) : "f"(s[i]));
            asm volatile("mov.b32 %0, %1;" : "=f"(gb[i]) : "f"(o[i]));
          }
#pragma unroll 1
          for (int i = 0; i < nst; i++) {
            mbar_wait(gfull + (i & 3) * 8, (i >> 2) & 1);
            const uint64_t da = make_desc(base + unit_of(xt, i & 3) + wg * 8192, 16, 1024), db = make_desc(base + unit_of(wt, i & 3), 8192, 1024);
            if (i == nst - 1) bar_sync(2 + wg, 256);
            wg_fence();
#pragma unroll
            for (int kk = 0; kk < 4; kk++) mma256_ss(ga, gb, da + kk * 2, db + kk * 128, kk ? 1 : i);
            wg_commit();
            if (i == nst - 1) bar_arrive(3 - wg, 256);
            wg_wait<1>();
            mbar_arrive_cl(rempty, GE + ((i + 3) & 3) * 8, i != 0);
            PROF(4, tid == 0 && (i & 3) == 0, 40 + (ps - 1) * 4 + i / 4);
          }
          wg_wait<0>();
          keep(ga); keep(gb);
#pragma unroll
          for (int i = 0; i < 64; i++) {
            asm volatile("mov.b32 %0, %1;" : "=f"(s[i]) : "f"(ga[i]));
            asm volatile("mov.b32 %0, %1;" : "=f"(o[i]) : "f"(gb[i]));
          }
        }
        mbar_arrive_cl(rempty, GE + (ps == 2 ? 24 : 8));
        if (ps == 2) break;
      }
      const uint32_t qw = base + wg * 8192, qt = QT >> (16 * ps), at = ps ? AT1 : AT0;
      {
        const uint32_t wt = ps ? WT1 : WT0;
        const uint64_t da0 = make_desc(qw + unit_of(qt, 2), 16, 1024), da1 = make_desc(qw + unit_of(qt, 3), 16, 1024);
        const uint64_t db0 = make_desc(base + unit_of(wt, 2), 8192, 1024), db1 = make_desc(base + unit_of(wt, 3), 8192, 1024);
        mbar_wait(gfull + 16, 1);
        bar_sync(2 + wg, 256);
        wg_fence();
#pragma unroll
        for (int kk = 0; kk < 4; kk++) mma_ss<1>(s, da0 + kk * 2, db0 + kk * 128, 1);
        wg_commit();
        mbar_wait(xfull + 24, 1);
        mbar_wait(gfull + 24, 1);
        wg_fence();
#pragma unroll
        for (int kk = 0; kk < 4; kk++) mma_ss<1>(s, da1 + kk * 2, db1 + kk * 128, 1);
        wg_commit();
        bar_arrive(3 - wg, 256);
        mbar_wait(ps == 0 ? bar_pread : bar_ofree + 8, 0);
        wg_wait<0>();
        keep(s);
        PROF(2, tid == 0, 8 + ps * 8);
        uint32_t q[32];
        pack_p(s, q);
#pragma unroll
        for (int i = 0; i < 4; i++) stmatrix4((qw + unit_of(qt, 0) + frag_offset(warp)) ^ (i << 5), q[4 * i], q[4 * i + 1], q[4 * i + 2], q[4 * i + 3]);
        keep(q);
        bar_sync(2 + wg, 256);
        wg_fence();
#pragma unroll
        for (int kk = 0; kk < 8; kk++) mma_ss<1>(o, (kk < 4 ? da0 : da1) + (kk & 3) * 2, (kk < 4 ? db0 : db1) + UNIT / 16 + (kk & 3) * 128, 1);
        wg_commit();
        mbar_wait(bfull, 0);
        wg_fence();
        const uint64_t dk = make_desc(base + unit_of(at, 0), 16, 1024);
#pragma unroll
        for (int kk = 0; kk < 8; kk++) mma_rs<0>(s, q[4 * kk], q[4 * kk + 1], q[4 * kk + 2], q[4 * kk + 3], dk + (kk >> 2) * 1024 + (kk & 3) * 2, kk != 0);
        wg_commit();
        bar_arrive(3 - wg, 256);
#pragma unroll
        for (int i = 4; i < 8; i++) stmatrix4((qw + unit_of(qt, 1) + frag_offset(warp)) ^ ((i & 3) << 5), q[4 * i], q[4 * i + 1], q[4 * i + 2], q[4 * i + 3]);
        wg_wait<1>();
        keep(o);
        mbar_arrive_cl(rempty, GE + 16);
        mbar_arrive_cl(rempty, GE + 24);
        store_chunk<0>(o, qw + unit_of(qt, 2) + frag_offset(warp));
        store_chunk<1>(o, qw + unit_of(qt, 3) + frag_offset(warp));
        wg_wait<0>();
        keep(s);
        mbar_arrive_cl(rempty, 0);
      }
      PROF(4, tid == 0 && ps == 1, 61);
      float l0 = 0.f, l1 = 0.f;
      auto step = [&](auto odd_c, const int j, uint32_t (&pw)[32], uint32_t (&pr)[32]) {
        constexpr bool ODD = decltype(odd_c)::value;
        const bool first = !ODD && (j & 2) == 0, last = ODD && j == 7;
        const uint32_t ph = (j >> 1) & 1;
        float i0, i1, a0, a1;
        const bool so = !ODD && j == 4;
        if (so) { i0 = inv_quad_sum(l0); i1 = inv_quad_sum(l1); l0 = 0.f; l1 = 0.f; }
        bool redo = !ODD && (j | ps) == 0;
        while (true) {
          if (redo) {
            float m0 = fmaxf(s[0], s[1]), m1 = fmaxf(s[2], s[3]);
#pragma unroll
            for (int i = 1; i < 16; i++) { m0 = fmaxf(m0, fmaxf(s[4 * i], s[4 * i + 1])); m1 = fmaxf(m1, fmaxf(s[4 * i + 2], s[4 * i + 3])); }
            m0 = fmaxf(m0, __shfl_xor_sync(0xffffffffu, m0, 1)); m1 = fmaxf(m1, __shfl_xor_sync(0xffffffffu, m1, 1));
            m0 = fmaxf(m0, __shfl_xor_sync(0xffffffffu, m0, 2)); m1 = fmaxf(m1, __shfl_xor_sync(0xffffffffu, m1, 2));
            m0 *= SCL2; m1 *= SCL2;
            if (!first) {
              m0 = fmaxf(m0, f0); m1 = fmaxf(m1, f1);
              const float c0 = ex2(f0 - m0), c1 = ex2(f1 - m1);
              l0 *= c0; l1 *= c1;
              wg_wait<0>();
              keep(o);
#pragma unroll
              for (int i = 0; i < 16; i++) { o[4 * i] *= c0; o[4 * i + 1] *= c0; o[4 * i + 2] *= c1; o[4 * i + 3] *= c1; }
            }
            f0 = m0; f1 = m1;
          }
          float b0 = 0.f, b1 = 0.f;
          a0 = 0.f; a1 = 0.f;
#pragma unroll
          for (int i = 0; i < 16; i++) {
            const float e0 = ex2(fmaf(s[4 * i], SCL2, -f0)), e1 = ex2(fmaf(s[4 * i + 1], SCL2, -f0));
            const float e2 = ex2(fmaf(s[4 * i + 2], SCL2, -f1)), e3 = ex2(fmaf(s[4 * i + 3], SCL2, -f1));
            a0 += e0; b0 += e1; a1 += e2; b1 += e3;
            pw[2 * i] = pack_bf(e0, e1); pw[2 * i + 1] = pack_bf(e2, e3);
            if (i == VREL) {
#pragma unroll
              for (int k = 0; k < 2 * VREL + 2; k++) asm volatile("" : "+r"(pw[k])::"memory");
              mbar_wait(bar_mod, 0);
              wg_wait<0>();
              mbar_arrive_cl(rempty, ODD ? 16 : 0, !redo && (ODD || j));
#pragma unroll
              for (int k = 4 * VREL + 4; k < 64; k++) asm volatile("" : "+f"(s[k])::"memory");
            }
          }
          a0 += b0; a1 += b1;
          if (redo) break;
          redo = __any_sync(0xffffffffu, !(a0 + a1 < 0x1p90f));
          if (first) {
            uint32_t m0 = __ballot_sync(0xffffffffu, a0 > 0x1p-80f), m1 = __ballot_sync(0xffffffffu, a1 > 0x1p-80f);
            m0 |= m0 >> 1; m1 |= m1 >> 1; m0 |= m0 >> 2; m1 |= m1 >> 2;
            redo = redo || (m0 & m1 & 0x11111111u) != 0x11111111u;
          }
          if (!redo) break;
        }
        l0 += a0; l1 += a1;
        keep(pw);
        keep(o);
        if (so) store_chunk<0>(o, i0, i1, qw + unit_of(qt, 0) + frag_offset(warp));
        keep(o);
        if (j == (ODD ? 5 : 0)) { fence_async_smem(); if (ODD) mbar_arrive(bar_ofull + wg * 8); }
        mbar_wait(bfull + (ODD ? 24 : 8), ph);
        bar_sync(2 + wg, 256);
        if (!last) {
          const uint32_t qn = qt >> (j >= 3 ? 8 : 0);
          wg_fence();
          issue_qk(s, qw + unit_of(qn, 0), qw + unit_of(qn, 1), base + unit_of(at, ODD ? 3 : 1));
          wg_commit();
          mbar_wait(bfull + (ODD ? 0 : 16), ODD ? ph ^ 1 : ph);
        }
        if (so) { store_chunk<1>(o, i0, i1, qw + unit_of(qt, 1) + frag_offset(warp)); keep(o); }
        wg_fence();
        issue_pv(o, pw, base + unit_of(at, ODD ? (last ? 3 : 0) : 2), !first);
        wg_commit();
        bar_arrive(3 - wg, 256);
        wg_wait<1>();
        keep(s);
        mbar_arrive_cl(rempty, ODD ? 24 : 8, !last);
        PROF(4, tid == 0 && ps == 1, 51 + j);
      };
      uint32_t pa[32], pb[32];
#pragma unroll 1
      for (int j = 0; j < 8; j += 2) {
        step(std::false_type{}, j, pa, pb);
        step(std::true_type{}, j + 1, pb, pa);
      }
      {
        const float i0 = inv_quad_sum(l0), i1 = inv_quad_sum(l1);
        wg_wait<0>();
        keep(o);
        mbar_arrive_cl(rempty, 24);
        store_chunk<0>(o, i0, i1, qw + unit_of(qt, 2) + frag_offset(warp));
        store_chunk<1>(o, i0, i1, qw + unit_of(qt, 3) + frag_offset(warp));
        fence_async_smem();
        mbar_arrive(bar_ofull + 16 + wg * 8);
      }
      PROF(2, tid == 0, 10 + ps * 8);
    }

    const int ln = fresh_lane(), g = ln >> 2, tq = ln & 3, ct = warp * 32 + ln;
    const bool lane0 = ln == 0;
    const int lrow0 = warp * 16 + g;
    const int grow0 = rb * 128 + lrow0;
    const uint32_t res = base + OFF_RES, trow = res + wg * 8192 + frag_offset(warp);
    uint32_t xr[32];
    uint4 sv[4], own;
    uint32_t* sp[4];
#pragma unroll
    for (int k = 0; k < 4; k++) sp[k] = g_stats + ((((tq >> 1) * 4 + k) ^ cj) * SEQ + grow0 + (tq & 1) * 8) * 4;
    {
      const uint64_t da = make_desc(base + wg * 8192, 16, 1024), db = make_desc(base, 8192, 1024);
      constexpr int U = UNIT / 16;
#define HALF_STAGE(acc, xu, wu) _Pragma("unroll") for (int kk = 0; kk < 4; kk++) mma_ss<1>(acc, da + (xu) * U + kk * 2, db + (wu) * U + kk * 128, 1)
      PROF(10, ct == PT, 19); STAMP(0);
      cluster_arrive();
      mbar_wait(gfull, 1);
      mbar_wait(gfull + 8, 1);
      bar_sync(2 + wg, 256);
      wg_fence();
      HALF_STAGE(o, 7, 1);
      HALF_STAGE(o, 8, 3);
      wg_commit();
      STAMP(16);
      mbar_wait(gfull + 16, 1);
      STAMP(17);
      wg_fence();
      HALF_STAGE(o, 6, 11);
      wg_commit();
      bar_arrive(3 - wg, 256);
      mbar_wait(bar_par, 0);
      uint32_t* xo = g_xch + ((size_t)b * 8 * 256 + ct) * 4;
      const uint32_t* xi = g_xch + ((size_t)(b ^ 2) * 8 * 256 + ct) * 4;
      const uint32_t par1 = (~lds1(par + PAR_CONST + 4) & 1) << 16;
      wg_wait<1>();
      mbar_arrive_pred(bar_rel, lane0);
      wg_wait<0>();
      keep(o);
      mbar_arrive_pred(bar_ring, lane0);
      PROF(8, ct == PT, 20); STAMP(1);
#define SEND(i) st_b128(xo + (i) * 1024, (pack_bf(o[8 * (i)], o[8 * (i) + 1]) & ~0x10000u) | par1, pack_bf(o[8 * (i) + 2], o[8 * (i) + 3]), \
                        pack_bf(o[8 * (i) + 4], o[8 * (i) + 5]), pack_bf(o[8 * (i) + 6], o[8 * (i) + 7]))
#pragma unroll
      for (int i = 0; i < NS1; i++) SEND(i);
      PROF(8, ct == PT, 21); STAMP(2);
      bar_sync(2 + wg, 256);
      wg_fence();
      HALF_STAGE(s, 7, 0);
      HALF_STAGE(s, 8, 2);
      HALF_STAGE(s, 6, 10);
      wg_commit();
      bar_arrive(3 - wg, 256);
      STAMP(18);
      mbar_wait(gfull + 24, 1);
#pragma unroll
      for (int i = NS1; i < 8; i++) SEND(i);
      uint4 v[8];
#pragma unroll
      for (int i = 0; i < LD1; i++) v[i] = ld_b128(xi + i * 1024);
      STAMP(19);
      mbar_wait(bar_xres, 0);
      wg_wait<0>();
      mbar_arrive_pred(bar_ring + 8, lane0);
      bar_sync(2 + wg, 256);
      STAMP(20);
#pragma unroll
      for (int i = LD1; i < LD2; i++) v[i] = ld_b128(xi + i * 1024);
      mbar_wait(bar_xres, 0);
      wg_fence();
      HALF_STAGE(s, 9, 4);
      wg_commit();
      mbar_wait(bar_rx, 0);
      wg_fence();
      HALF_STAGE(s, 1, 5);
      wg_commit();
      bar_arrive(3 - wg, 256);
      STAMP(21);
#pragma unroll
      for (int i = LD2; i < 8; i++) v[i] = ld_b128(xi + i * 1024);
      if (LD2 < 8) mbar_wait(bar_xres, 0);
      wg_wait<0>();
      keep(s);
      mbar_arrive_pred(bar_ring + 16, lane0);
      PROF(10, ct == PT, 23); STAMP(4);
#pragma unroll
      for (int i = 0; i < 16; i += 2) ldmatrix4((trow ^ ((i & 7) << 4)) + (i >> 3) * 16384, xr[2 * i], xr[2 * i + 1], xr[2 * i + 2], xr[2 * i + 3]);
      uint32_t ga[16];
      uint4 bw[8];
#pragma unroll
      for (int i = 0; i < 8; i++) {
        if (!(i & 1)) {
          const uint4 t = lds4(par + PAR_SINK + i * 32 + tq * 16);
          ga[2 * i] = t.x; ga[2 * i + 1] = t.y; ga[2 * i + 2] = t.z; ga[2 * i + 3] = t.w;
        }
        bw[i] = lds4(par + PAR_T1 + i * 64 + tq * 16);
        if (!(g & 1)) { bw[i].x = 0x3f803f80u; bw[i].y = 0x3f803f80u; }
      }
      uint32_t pk[32];
      pack_p(s, pk);
      keep(pk);
      {
        uint32_t n = 0, miss;
        do {
          miss = 0;
#pragma unroll
          for (int i = 0; i < 8; i++) miss |= v[i].x ^ par1;
          miss = __any_sync(0xffffffffu, miss & 0x10000u);
          if (miss) {
#pragma unroll
            for (int i = 0; i < 8; i++)
              asm volatile("{ .reg .pred p; .reg .b32 t; xor.b32 t, %0, %5; and.b32 t, t, 0x10000; setp.ne.u32 p, t, 0;\n"
                           "@p ld.relaxed.gpu.global.v4.u32 {%0, %1, %2, %3}, [%4]; }"
                           : "+r"(v[i].x), "+r"(v[i].y), "+r"(v[i].z), "+r"(v[i].w) : "l"(xi + i * 1024), "r"(par1) : "memory");
          }
          watchdog(n);
        } while (miss);
      }
      PROF(8, ct == PT, 22); STAMP(3);
      float ds[4] = {0.f, 0.f, 0.f, 0.f}, dl[4] = {0.f, 0.f, 0.f, 0.f}, q0[4] = {0.f, 0.f, 0.f, 0.f}, q1[4] = {0.f, 0.f, 0.f, 0.f};
#pragma unroll
      for (int i = 0; i < 8; i++) {
        const uint32_t u0 = hfma2(ga[2 * i], hadd2(pk[4 * i], v[i].x & ~0x10000u), xr[4 * i]);
        const uint32_t u1 = hfma2(ga[2 * i], hadd2(pk[4 * i + 1], v[i].y), xr[4 * i + 1]);
        const uint32_t u2 = hfma2(ga[2 * i + 1], hadd2(pk[4 * i + 2], v[i].z), xr[4 * i + 2]);
        const uint32_t u3 = hfma2(ga[2 * i + 1], hadd2(pk[4 * i + 3], v[i].w), xr[4 * i + 3]);
        xr[4 * i] = u0; xr[4 * i + 1] = u1; xr[4 * i + 2] = u2; xr[4 * i + 3] = u3;
        mma16816(ds, u0, u1, u2, u3, bw[i].x, bw[i].y);
        mma16816(dl, u0, u1, u2, u3, bw[i].z, bw[i].w);
        mma16816(q0, u0, u1, u2, u3, u0, u2);
        mma16816(q1, u0, u1, u2, u3, u1, u3);
      }
      const float sqa = __shfl_sync(0xffffffffu, (g & 1) ? q0[1] : q0[0], g * 4 + (g >> 1));
      const float sqb = __shfl_sync(0xffffffffu, (g & 1) ? q1[3] : q1[2], g * 4 + (g >> 1));
      own = (tq & 1) ? make_uint4(__float_as_uint(ds[2]), __float_as_uint(sqb), __float_as_uint(ds[3] + dl[3]), tag)
                                 : make_uint4(__float_as_uint(ds[0]), __float_as_uint(sqa), __float_as_uint(ds[1] + dl[1]), tag);
      if (tq < 2) st_b128(sp[0], own.x, own.y, own.z, own.w);
#pragma unroll
      for (int k = 0; k < 4; k++) sv[k] = make_uint4(0, 0, 0, 0);
    }
    PROF(8, ct == PT, 29); STAMP(5);
    uint32_t mm, ih, il;
    float rbest;
    uint32_t wf[128];
    const uint32_t frow = (ln & 7) + (ln >> 4) * 8;
    const uint32_t wfo = base + (warp & 1) * 8192 + frow * 64 + ((((ln >> 3) & 1) ^ ((frow >> 1) & 3)) << 4);
#define LOAD_WF(m) _Pragma("unroll") for (int f = 0; f < 16; f++) {                                                   \
      const int r = ((f >> 1) * 4 + (m) * 2 + (f & 1)) * 4;                                                           \
      ldmatrix4t(((wfo + unit_of((m) ? FT_U : FT_G, warp >> 1)) ^ ((f & 1) * 32)) + (f >> 1) * 1024, wf[r], wf[r + 1], wf[r + 2], wf[r + 3]); \
    }
    bool early;
    {
#pragma unroll
      for (int i = 0; i < 16; i += 2) stmatrix4((trow ^ ((i & 7) << 4)) + (i >> 3) * 16384, xr[2 * i], xr[2 * i + 1], xr[2 * i + 2], xr[2 * i + 3]);
      const uint4 cst = lds4(par + PAR_CONST);
      const float A1 = __uint_as_float(cst.x), A2 = __uint_as_float(cst.z);
      uint32_t n = 0;
      early = false;
#pragma unroll 1
      while (true) {
        uint32_t miss;
        asm volatile("{ .reg .pred p0, p1, p2, p3; .reg .b64 u, v; .reg .b128 w;\n"
                     "setp.ge.u32 p0, %22, 2; setp.ne.and.u32 p0, %4, %21, p0; setp.ne.u32 p1, %8, %21; setp.ne.u32 p2, %12, %21; setp.ne.u32 p3, %16, %21;\n"
                     "@p0 ld.relaxed.gpu.global.v4.u32 {%1, %2, %3, %4}, [%17];\n"
                     "@p1 ld.relaxed.gpu.global.v4.u32 {%5, %6, %7, %8}, [%18];\n"
                     "@p2 ld.relaxed.gpu.global.v4.u32 {%9, %10, %11, %12}, [%19];\n"
                     "@p3 ld.relaxed.gpu.global.v4.u32 {%13, %14, %15, %16}, [%20];\n"
                     "or.pred p0, p0, p1; or.pred p2, p2, p3; or.pred p0, p0, p2; vote.sync.any.pred p0, p0, 0xffffffff; selp.u32 %0, 1, 0, p0; }"
                     : "=r"(miss), "+r"(sv[0].x), "+r"(sv[0].y), "+r"(sv[0].z), "+r"(sv[0].w), "+r"(sv[1].x), "+r"(sv[1].y), "+r"(sv[1].z), "+r"(sv[1].w),
                       "+r"(sv[2].x), "+r"(sv[2].y), "+r"(sv[2].z), "+r"(sv[2].w), "+r"(sv[3].x), "+r"(sv[3].y), "+r"(sv[3].z), "+r"(sv[3].w)
                     : "l"(sp[0]), "l"(sp[1]), "l"(sp[2]), "l"(sp[3]), "r"(tag), "r"(tq) : "memory");
        if (!miss) break;
        if (!early && (b >= NFFN || __all_sync(0xffffffffu, mbar_test(bar_box + (warp >> 1) * 8, 0)))) {
          early = true;
          LOAD_WF(0);
          __syncwarp();
          mbar_arrive_pred(bar_gate, lane0);
        }
        watchdog(n);
      }
      const uint4 v0 = tq < 2 ? own : sv[0], v1 = sv[1], v2 = sv[2], v3 = sv[3];
      PROF(8, ct == PT, 30); STAMP(6);
      float su = (__uint_as_float(v0.x) + __uint_as_float(v1.x)) + (__uint_as_float(v2.x) + __uint_as_float(v3.x));
      float sq = (__uint_as_float(v0.y) + __uint_as_float(v1.y)) + (__uint_as_float(v2.y) + __uint_as_float(v3.y));
      float dt = (__uint_as_float(v0.z) + __uint_as_float(v1.z)) + (__uint_as_float(v2.z) + __uint_as_float(v3.z));
      su += __shfl_xor_sync(0xffffffffu, su, 2); sq += __shfl_xor_sync(0xffffffffu, sq, 2); dt += __shfl_xor_sync(0xffffffffu, dt, 2);
      const float m = su * (1.f / DM);
      float mb, sd;
      ln_scalars(m, fmaxf(sq * (1.f / DM) - m * m, 0.f), mb, sd);
      const float inv = rcp(sd);
      rbest = (dt - mb * A1) * inv + A2;
      mm = pack_bf(mb, mb);
      ih = pack_bf(inv, inv);
      const float lo = inv - bf_lo(ih);
      il = pack_bf(lo, lo);
    }
    int ibest;
    {
      const uint32_t bits = __float_as_uint(rbest);
      const uint32_t key = (((int)bits < 0 ? ~bits : bits | 0x80000000u) & ~0x1ffu) | ((127 - lrow0 - (tq & 1) * 8) << 2) | tag;
      sts1(par + PAR_RED + warp * 4, __reduce_max_sync(0xffffffffu, key));
      PROF(8, ct == PT, 38); STAMP(7);
      bar_sync(1, 256);
      const uint4 ka = lds4(par + PAR_RED), kb = lds4(par + PAR_RED + 16);
      const uint32_t k2 = max(max(max(ka.x, ka.y), max(ka.z, ka.w)), max(max(kb.x, kb.y), max(kb.z, kb.w)));
      if (ct == 0 && cj == 0) st_relaxed(g_cand + rb, k2);
      ibest = 127 - ((k2 >> 2) & 127);
    }
    PROF(8, ct == PT, 39); STAMP(8);
    if ((ibest >> 4) == warp) {
      const int src = (ibest & 7) * 4 + ((ibest >> 3) & 1), ch = g * 2;
      const uint32_t cm = __shfl_sync(0xffffffffu, mm, src), ch_ = __shfl_sync(0xffffffffu, ih, src), cl = __shfl_sync(0xffffffffu, il, src);
      const uint32_t xa = res + (ch >> 3) * 16384 + ibest * 128 + (((ch & 7) ^ (ibest & 7)) << 4) + tq * 4;
      const uint32_t x0 = lds1(xa), x1 = lds1(xa ^ 16);
      const uint2 p0 = lds2(par + PAR_T2 + ch * 64 + tq * 16), p1 = lds2(par + PAR_T2 + ch * 64 + 64 + tq * 16);
      uint32_t* dst = g_row + rb * 2 * DM + cj * 128 + ln * 4;
      st_pairs(dst, ln_mod(x0, cm, ch_, cl, p0.x, p0.y), ln_mod(x1, cm, ch_, cl, p1.x, p1.y), tag);
      st_pairs(dst + DM, x0, x1, tag);
      __syncwarp();
    }
    PROF(8, ct == PT, 37); STAMP(9);
    uint32_t wd[64];
    const uint32_t wda = base + unit_of(FT_D, warp >> 1) + (warp & 1) * 8192 + frow * 128 + ((((ln >> 3) & 1) ^ (ln & 7)) << 4);
#define LOAD_WD(f) ldmatrix4t((wda ^ ((((f) >> 1) & 3) * 32)) + ((f) >> 3) * 4096 + ((f) & 1) * 2048, wd[4 * (f)], wd[4 * (f) + 1], wd[4 * (f) + 2], wd[4 * (f) + 3])
    if (!early) {
      if (b < NFFN) mbar_wait(bar_box + (warp >> 1) * 8, 0);
      LOAD_WF(0);
      __syncwarp();
      mbar_arrive_pred(bar_gate, lane0);
    }
    if (b < NFFN) {
      const uint32_t own = base + unit_of(FT_G, warp >> 1) + (warp & 1) * 8192;
      mbar_wait(bar_box + (4 + (warp >> 1)) * 8, 0);
      LOAD_WF(1);
      uint32_t* const ydst = g_ypart + ((size_t)(warp * 16 + tq * 2) * NFFN + b) * 8 + g;
      PROF(8, ct == PT, 31); STAMP(10);
      bool wdok;
      {
        uint32_t n = 0;
        while (!(wdok = __all_sync(0xffffffffu, mbar_test(bar_box + (8 + (warp >> 1)) * 8, 0))) && !__all_sync(0xffffffffu, mbar_test(bar_sel, 0))) watchdog(n);
      }
      if (wdok) {
#pragma unroll
        for (int f = 0; f < 16; f++) LOAD_WD(f);
      }
      STAMP(11);
      mbar_wait(bar_sel, 0);
      PROF(8, ct == PT, 33); STAMP(12);
      float d[8][4];
#pragma unroll
      for (int i = 0; i < 4; i++) { d[i][0] = 0.f; d[i][1] = 0.f; d[i][2] = 0.f; d[i][3] = 0.f; }
#pragma unroll
      for (int ks = 0; ks < 8; ks++) {
        const uint2 hb = lds2(own + 256 + ks * 32 + tq * 8);
#pragma unroll
        for (int mt = 0; mt < 4; mt++) {
          const int r = ks * 16 + mt * 4;
          mma16816(d[mt], wf[r], wf[r + 1], wf[r + 2], wf[r + 3], hb.x, hb.y);
        }
      }
      sts2(own + (tq * 8 + g) * 8, __float_as_uint((tq & 2) ? ((tq & 1) ? d[1][2] : d[1][0]) : ((tq & 1) ? d[0][2] : d[0][0])),
           __float_as_uint((tq & 2) ? ((tq & 1) ? d[3][2] : d[3][0]) : ((tq & 1) ? d[2][2] : d[2][0])));
      bar_sync(1, 256);
      uint32_t ab[4];
      {
        float G = 0.f, U = 0.f;
        uint2 pv[8];
#pragma unroll
        for (int w8 = 0; w8 < 8; w8++) pv[w8] = lds2(base + ln * 8 + ((FT_G >> (w8 >> 1) * 4) & 15) * UNIT + (w8 & 1) * 8192);
#pragma unroll
        for (int w8 = 0; w8 < 8; w8 += 2) {
          G += __uint_as_float(pv[w8].x) + __uint_as_float(pv[w8 + 1].x);
          U += __uint_as_float(pv[w8].y) + __uint_as_float(pv[w8 + 1].y);
        }
        const float act = rbf(silu_f(rbf(G))) * rbf(U);
        const uint32_t pk = pack_bf(act, __shfl_down_sync(0xffffffffu, act, 1));
#pragma unroll
        for (int i = 0; i < 4; i++) ab[i] = __shfl_sync(0xffffffffu, pk, i * 8 + tq * 2);
      }
      if (!wdok) {
        mbar_wait(bar_box + (8 + (warp >> 1)) * 8, 0);
#pragma unroll
        for (int f = 0; f < 16; f++) LOAD_WD(f);
      }
      PROF(8, ct == PT, 34); STAMP(13);
#pragma unroll
      for (int mt = 0; mt < 8; mt++) {
        d[mt][0] = 0.f; d[mt][1] = 0.f; d[mt][2] = 0.f; d[mt][3] = 0.f;
        mma16816(d[mt], wd[mt * 8], wd[mt * 8 + 1], wd[mt * 8 + 2], wd[mt * 8 + 3], ab[0], ab[1]);
        mma16816(d[mt], wd[mt * 8 + 4], wd[mt * 8 + 5], wd[mt * 8 + 6], wd[mt * 8 + 7], ab[2], ab[3]);
      }
#pragma unroll
      for (int i = 0; i < 4; i++) {
        const int m4 = (i >> 1) * 4, e = (i & 1) * 2;
        const float y = (tq & 2) ? ((tq & 1) ? d[m4 + 3][e] : d[m4 + 2][e]) : ((tq & 1) ? d[m4 + 1][e] : d[m4][e]);
        st_relaxed(ydst + (m4 * 2 + (i & 1)) * NFFN * 8, tagf(y, tag));
      }
      PROF(8, ct == PT, 35); STAMP(14);
    }
    mbar_wait(bar_sel, 0);
    mbar_arrive_pred(bar_win, ct == 0);
    const int iwin = lds1(par + PAR_CONST + 60) & 0x7ff;
    const bool cand = (iwin >> 4) == rb * 8 + warp;
    {
      const uint32_t mm0 = __shfl_sync(0xffffffffu, mm, ln & ~1), mm1 = __shfl_sync(0xffffffffu, mm, ln | 1);
      const uint32_t ih0 = __shfl_sync(0xffffffffu, ih, ln & ~1), ih1 = __shfl_sync(0xffffffffu, ih, ln | 1);
      const uint32_t il0 = __shfl_sync(0xffffffffu, il, ln & ~1), il1 = __shfl_sync(0xffffffffu, il, ln | 1);
#pragma unroll 1
      for (int hf = 0; hf < 2; hf++) {
        uint32_t x[16];
#pragma unroll
        for (int i = 0; i < 8; i += 2) ldmatrix4((trow ^ (i << 4)) + hf * 16384, x[2 * i], x[2 * i + 1], x[2 * i + 2], x[2 * i + 3]);
#pragma unroll
        for (int i = 0; i < 8; i++) {
          const uint4 pv = lds4(par + PAR_T2 + (hf * 8 + i) * 64 + tq * 16);
          x[2 * i] = hadd2(x[2 * i], hmul2(pv.z, ln_mod(x[2 * i], mm0, ih0, il0, pv.x, pv.y)));
          x[2 * i + 1] = hadd2(x[2 * i + 1], hmul2(pv.z, ln_mod(x[2 * i + 1], mm1, ih1, il1, pv.x, pv.y)));
        }
#pragma unroll
        for (int i = 0; i < 8; i += 2) stmatrix4((trow ^ (i << 4)) + hf * 16384, x[2 * i], x[2 * i + 1], x[2 * i + 2], x[2 * i + 3]);
      }
      if (!cand) fence_async_smem();
      __syncwarp();
      if (!cand && elect_one()) {
        tma2d_store(&maps.out, res + warp * 2048, cj * 128, rb * 128 + warp * 16);
        tma2d_store(&maps.out, res + 16384 + warp * 2048, cj * 128 + 64, rb * 128 + warp * 16);
        asm volatile("cp.async.bulk.commit_group;" ::: "memory");
      }
    }
    if (cand) {
      const int wrow0 = warp * 16;
#pragma unroll 2
      for (int p = 0; p < 8; p++) {
        const int row = 2 * p + (ln >> 4), ch = ln & 15;
        const uint4 v = lds4(res + (ch >> 3) * 16384 + (wrow0 + row) * 128 + (((ch & 7) ^ (row & 7)) << 4));
        if (rb * 128 + wrow0 + row != iwin) *reinterpret_cast<uint4*>(P.out + (size_t)(rb * 128 + wrow0 + row) * DM + cj * 128 + ch * 8) = v;
      }
    }
    asm volatile("cp.async.bulk.wait_group.read 0;" ::: "memory");
    PROF(8, ct == PT, 11); STAMP(15);
    cluster_wait();
  }
}

typedef CUresult (*EncodeFn)(CUtensorMap*, CUtensorMapDataType, cuuint32_t, void*, const cuuint64_t*, const cuuint64_t*,
                             const cuuint32_t*, const cuuint32_t*, CUtensorMapInterleave, CUtensorMapSwizzle,
                             CUtensorMapL2promotion, CUtensorMapFloatOOBfill);

void map2d(EncodeFn enc, CUtensorMap* m, const void* p, uint64_t rows, uint64_t cols, uint32_t brows) {
  cuuint64_t dims[2] = {cols, rows}, strides[1] = {cols * 2};
  cuuint32_t box[2] = {64, brows}, es[2] = {1, 1};
  enc(m, CU_TENSOR_MAP_DATA_TYPE_BFLOAT16, 2, const_cast<void*>(p), dims, strides, box, es, CU_TENSOR_MAP_INTERLEAVE_NONE,
      CU_TENSOR_MAP_SWIZZLE_128B, CU_TENSOR_MAP_L2_PROMOTION_L2_256B, CU_TENSOR_MAP_FLOAT_OOB_FILL_NONE);
}
void map2d_narrow(EncodeFn enc, CUtensorMap* m, const void* p, uint64_t rows, uint64_t cols, uint32_t brows) {
  cuuint64_t dims[2] = {cols, rows}, strides[1] = {cols * 2};
  cuuint32_t box[2] = {32, brows}, es[2] = {1, 1};
  enc(m, CU_TENSOR_MAP_DATA_TYPE_BFLOAT16, 2, const_cast<void*>(p), dims, strides, box, es, CU_TENSOR_MAP_INTERLEAVE_NONE,
      CU_TENSOR_MAP_SWIZZLE_64B, CU_TENSOR_MAP_L2_PROMOTION_L2_64B, CU_TENSOR_MAP_FLOAT_OOB_FILL_NONE);
}
void map3d(EncodeFn enc, CUtensorMap* m, const void* p, uint64_t rows, uint64_t cols, uint32_t brows, uint32_t nch) {
  cuuint64_t dims[3] = {64, rows, cols / 64}, strides[2] = {cols * 2, 128};
  cuuint32_t box[3] = {64, brows, nch}, es[3] = {1, 1, 1};
  enc(m, CU_TENSOR_MAP_DATA_TYPE_BFLOAT16, 3, const_cast<void*>(p), dims, strides, box, es, CU_TENSOR_MAP_INTERLEAVE_NONE,
      CU_TENSOR_MAP_SWIZZLE_128B, CU_TENSOR_MAP_L2_PROMOTION_L2_256B, CU_TENSOR_MAP_FLOAT_OOB_FILL_NONE);
}

}

extern "C" void kernel_launch(void* const* d_in, const int* in_sizes, int n_in, void* d_out, int out_size) {
  (void)in_sizes; (void)n_in; (void)out_size;
  static EncodeFn enc = nullptr;
  if (!enc) {
    void* fn = nullptr;
    cudaDriverEntryPointQueryResult st;
    cudaGetDriverEntryPoint("cuTensorMapEncodeTiled", &fn, cudaEnableDefault, &st);
    enc = (EncodeFn)fn;
    cudaFuncSetAttribute(fused_kernel, cudaFuncAttributeMaxDynamicSharedMemorySize, SMEM_BYTES);
  }
  Maps maps;
  map2d(enc, &maps.x, d_in[0], SEQ, DM, 128);
  map2d(enc, &maps.out, d_out, SEQ, DM, 16);
  map3d(enc, &maps.wq, d_in[3], DM, NQ, 64, 2);
  map3d(enc, &maps.k, d_in[1], 4 * SK, 128, 128, 1);
  map3d(enc, &maps.v, d_in[2], 4 * SK, 128, 128, 1);
  map3d(enc, &maps.wo, d_in[4], NQ, DM, 64, 2);
  map2d_narrow(enc, &maps.wg, d_in[7], DM, FF, 256);
  map2d_narrow(enc, &maps.wu, d_in[8], DM, FF, 256);
  map3d(enc, &maps.wd, d_in[9], FF, DM, 32, 4);
  map2d_narrow(enc, &maps.wm, d_in[11], DM, NMOD, 256);
  Ptrs p;
  p.x = (const __nv_bfloat16*)d_in[0];
  p.w_r = (const __nv_bfloat16*)d_in[6];
  p.w_gate = (const __nv_bfloat16*)d_in[7];
  p.w_up = (const __nv_bfloat16*)d_in[8];
  p.w_down = (const __nv_bfloat16*)d_in[9];
  p.c = (const __nv_bfloat16*)d_in[10];
  p.w_mod = (const __nv_bfloat16*)d_in[11];
  p.out = (__nv_bfloat16*)d_out;
  fused_kernel<<<NMAIN + NHELP, 384, SMEM_BYTES>>>(maps, p);
}
```

```cpp
#include <cuda_runtime.h>
#include <cuda_bf16.h>
#include <cuda.h>
#include <stdint.h>
#include <type_traits>

#define HD 2
#define HDX 2
#define NRS 8
#define FPACE 3
#define GOST 20
#define WB 2
#define WN 20
#define RES0 17
#define RES1 20
#define HU 32
#define NS1 5
#define PG0 15
#define PSL 0
#define FB0 0
#define FB2 8
#define OPS 8192
#define OFL 0
#define ODS 8
#define MODUL hfma2
#define ODS1 5
#define LD1 0
#define LD2 4
#define FB1 2
#define FPB 8
#define FPACE0 2
#define OSL 900
#define OSL2 400
#define LNP 1
#define UPE 1
#define OMUL modul
#define VREL 5
#define E0 3

namespace {

constexpr int SEQ = 2048, DM = 1024, NQ = 4096, SK = 2048, WIN = 512, FF = 3584, NMOD = 6144;
constexpr int NMAIN = 128, NHELP = 4, NFFN = 112;
constexpr int NSLOT = 4, SLOT_BYTES = 32768, UNIT = 16384, GST_BYTES = 3 * UNIT;
constexpr uint32_t XT1 = 0xDCBA, XT2 = 0x9687;
constexpr uint32_t WT0 = 0xA741, WT1 = 0x7420, WT2 = 0x4A20;
constexpr uint32_t AT0 = WT1, AT1 = WT2;
constexpr uint32_t QT = 0xDC9696DC;
constexpr int OFF_STAGE = 12 * UNIT;
constexpr uint32_t FT_G = 0x07B3, FT_U = 0xA628, FT_D = 0x5149;
constexpr int OFF_RES = 12 * UNIT;
constexpr int OFF_PAR = 14 * UNIT;
constexpr int OFF_BAR = OFF_PAR + 2528;
constexpr int SMEM_BYTES = OFF_BAR + 544;
static_assert(SMEM_BYTES <= 232448, "smem");

constexpr int PAR_T1 = 0;
constexpr int PAR_T2 = 512;
constexpr int PAR_CONST = 1536;
constexpr int PAR_RED = 1600;
constexpr int PAR_SINK = 2176;

struct Maps {
  CUtensorMap x, wq, k, v, wo, wg, wu, wd, wm, out;
};
struct Ptrs {
  const __nv_bfloat16 *x, *w_r, *c, *w_mod, *w_gate, *w_up, *w_down;
  __nv_bfloat16* out;
};

__device__ __align__(1024) uint8_t g_act[16 * 80 * UNIT];
__device__ __align__(128) uint32_t g_mod[NMOD];
__device__ __align__(128) uint32_t g_modp[2 * 2 * DM];
__device__ __align__(128) uint32_t g_ln1[SEQ * 4];
__device__ __align__(128) uint32_t g_cnt_h[16 * 32];
__device__ __align__(128) uint32_t g_cnt_o[128 * 32];
__device__ __align__(128) uint32_t g_xch[NMAIN * 8 * 256 * 4];
__device__ __align__(128) uint32_t g_stats[8 * SEQ * 4];
__device__ __align__(128) uint32_t g_cand[32];
__device__ __align__(128) uint32_t g_row[16 * 2 * DM];
__device__ __align__(128) uint32_t g_ypart[NMAIN * NFFN * 8];
__device__ uint32_t g_epoch;

__device__ __forceinline__ uint32_t fresh_lane() { uint32_t l; asm volatile("mov.u32 %0, %%laneid;" : "=r"(l)); return l; }
__device__ __forceinline__ uint32_t frag_offset(int warp) {
  const uint32_t l = fresh_lane();
  return ((warp & 3) * 16 + (l & 15)) * 128 + (((l >> 4) ^ (l & 7)) << 4);
}
__device__ __forceinline__ bool elect_one() {
  uint32_t p;
  asm volatile("{ .reg .pred q; elect.sync _|q, 0xffffffff; selp.u32 %0, 1, 0, q; }" : "=r"(p));
  return p;
}
__device__ __forceinline__ uint32_t smem_u32(const void* p) { return (uint32_t)__cvta_generic_to_shared(p); }
__device__ __forceinline__ void mbar_init(uint32_t bar, uint32_t cnt) {
  asm volatile("mbarrier.init.shared::cta.b64 [%0], %1;" ::"r"(bar), "r"(cnt) : "memory");
}
__device__ __forceinline__ void mbar_expect_tx(uint32_t bar, uint32_t bytes) {
  asm volatile("mbarrier.arrive.expect_tx.shared::cta.b64 _, [%0], %1;" ::"r"(bar), "r"(bytes) : "memory");
}
__device__ __forceinline__ void mbar_arrive(uint32_t bar) {
  asm volatile("mbarrier.arrive.shared::cta.b64 _, [%0];" ::"r"(bar) : "memory");
}
__device__ __forceinline__ void mbar_arrive_pred(uint32_t bar, bool p) {
  asm volatile("{ .reg .pred p; setp.ne.b32 p, %1, 0; @p mbarrier.arrive.shared::cta.b64 _, [%0]; }" ::"r"(bar), "r"((int)p) : "memory");
}
__device__ __forceinline__ void mbar_arrive_cl(uint32_t bar, uint32_t off, bool p = true) {
  asm volatile("{ .reg .pred p, q; .reg .b32 a; setp.ne.b32 q, %2, 0; setp.ne.and.b32 p, %0, 0, q; add.u32 a, %0, %1; @p mbarrier.arrive.shared::cluster.b64 _, [a]; }"
               ::"r"(bar), "r"(off), "r"((int)p) : "memory");
}
__device__ __forceinline__ uint32_t mapa(uint32_t addr, uint32_t cta) {
  uint32_t r; asm("mapa.shared::cluster.u32 %0, %1, %2;" : "=r"(r) : "r"(addr), "r"(cta)); return r;
}
__device__ __forceinline__ void cluster_arrive() { asm volatile("barrier.cluster.arrive.relaxed.aligned;" ::: "memory"); }
__device__ __forceinline__ void cluster_wait() { asm volatile("barrier.cluster.wait.aligned;" ::: "memory"); }
__device__ __forceinline__ void watchdog(uint32_t& n) {
}
__device__ __forceinline__ void mbar_wait(uint32_t bar, uint32_t parity) {
  asm volatile("{\n.reg .pred p;\nWAIT_%=:\nmbarrier.try_wait.parity.shared::cta.b64 p, [%0], %1;\n@!p bra WAIT_%=;\n}" ::"r"(bar), "r"(parity) : "memory");
}
__device__ __forceinline__ bool mbar_test(uint32_t bar, uint32_t parity) {
  uint32_t ok;
  asm volatile("{\n.reg .pred p;\nmbarrier.test_wait.parity.shared::cta.b64 p, [%1], %2;\nselp.u32 %0, 1, 0, p;\n}" : "=r"(ok) : "r"(bar), "r"(parity) : "memory");
  return ok;
}
__device__ __forceinline__ uint64_t l2_stream() {
  uint64_t f; asm("createpolicy.fractional.L2::evict_first.b64 %0, 1.0;" : "=l"(f)); return f;
}
__device__ __forceinline__ void tma2d(uint32_t dst, const CUtensorMap* m, int c0, int c1, uint32_t bar) {
  asm volatile("cp.async.bulk.tensor.2d.shared::cluster.global.mbarrier::complete_tx::bytes.L2::cache_hint [%0], [%1, {%3, %4}], [%2], %5;"
               ::"r"(dst), "l"(m), "r"(bar), "r"(c0), "r"(c1), "l"(l2_stream()) : "memory");
}
__device__ __forceinline__ void bulk_load(uint32_t dst, const void* src, uint32_t bytes, uint32_t bar) {
  asm volatile("cp.async.bulk.shared::cluster.global.mbarrier::complete_tx::bytes [%0], [%1], %2, [%3];" ::"r"(dst), "l"(src), "r"(bytes), "r"(bar) : "memory");
}
__device__ __forceinline__ void bulk_load_stream(uint32_t dst, const void* src, uint32_t bytes, uint32_t bar) {
  asm volatile("cp.async.bulk.shared::cluster.global.mbarrier::complete_tx::bytes.L2::cache_hint [%0], [%1], %2, [%3], %4;"
               ::"r"(dst), "l"(src), "r"(bytes), "r"(bar), "l"(l2_stream()) : "memory");
}
__device__ __forceinline__ void tma2d_store(const CUtensorMap* m, uint32_t src, int c0, int c1) {
  asm volatile("cp.async.bulk.tensor.2d.global.shared::cta.bulk_group [%0, {%2, %3}], [%1];" ::"l"(m), "r"(src), "r"(c0), "r"(c1) : "memory");
}
__device__ __forceinline__ void bulk_store(void* dst, uint32_t src, uint32_t bytes) {
  asm volatile("cp.async.bulk.global.shared::cta.bulk_group [%0], [%1], %2;" ::"l"(dst), "r"(src), "r"(bytes) : "memory");
}
__device__ __forceinline__ int slice_of(int i) { return i + ((i & 7) == 1) - ((i & 7) == 2); }
__device__ __forceinline__ uint32_t unit_of(uint32_t table, uint32_t i) { return ((table >> (i * 4)) & 15) * UNIT; }
__device__ __forceinline__ void tma3d(uint32_t dst, const CUtensorMap* m, int c0, int c1, int c2, uint32_t bar) {
  asm volatile("cp.async.bulk.tensor.3d.shared::cluster.global.mbarrier::complete_tx::bytes.L2::cache_hint [%0], [%1, {%3, %4, %5}], [%2], %6;"
               ::"r"(dst), "l"(m), "r"(bar), "r"(c0), "r"(c1), "r"(c2), "l"(l2_stream()) : "memory");
}
template <bool STREAM>
__device__ __forceinline__ void tma3d_mc(uint32_t dst, const CUtensorMap* m, int c0, int c1, int c2, uint32_t bar) {
  if (STREAM)
    asm volatile("cp.async.bulk.tensor.3d.shared::cluster.global.mbarrier::complete_tx::bytes.multicast::cluster.L2::cache_hint [%0], [%1, {%3, %4, %5}], [%2], %6, %7;"
                 ::"r"(dst), "l"(m), "r"(bar), "r"(c0), "r"(c1), "r"(c2), "h"((uint16_t)3), "l"(l2_stream()) : "memory");
  else
    asm volatile("cp.async.bulk.tensor.3d.shared::cluster.global.mbarrier::complete_tx::bytes.multicast::cluster [%0], [%1, {%3, %4, %5}], [%2], %6;"
                 ::"r"(dst), "l"(m), "r"(bar), "r"(c0), "r"(c1), "r"(c2), "h"((uint16_t)3) : "memory");
}
__device__ __forceinline__ void prefetch_map(const CUtensorMap* m) {
  asm volatile("prefetch.tensormap [%0];" ::"l"(m) : "memory");
}
__device__ __forceinline__ void fence_async() { asm volatile("fence.proxy.async.global;" ::: "memory"); }
__device__ __forceinline__ void fence_async_smem() { asm volatile("fence.proxy.async.shared::cta;" ::: "memory"); }
__device__ __forceinline__ void bar_sync(int id, int n) { asm volatile("bar.sync %0, %1;" ::"r"(id), "r"(n) : "memory"); }
__device__ __forceinline__ void bar_arrive(int id, int n) { asm volatile("bar.arrive %0, %1;" ::"r"(id), "r"(n) : "memory"); }
__device__ __forceinline__ void wg_fence() { asm volatile("wgmma.fence.sync.aligned;" ::: "memory"); }
__device__ __forceinline__ void wg_commit() { asm volatile("wgmma.commit_group.sync.aligned;" ::: "memory"); }
template <int N> __device__ __forceinline__ void wg_wait() { asm volatile("wgmma.wait_group.sync.aligned %0;" ::"n"(N) : "memory"); }
__device__ __forceinline__ uint64_t make_desc(uint32_t addr, uint32_t lbo, uint32_t sbo) {
  return (uint64_t)((addr & 0x3FFFF) >> 4) | ((uint64_t)(lbo >> 4) << 16) | ((uint64_t)(sbo >> 4) << 32) | (1ull << 62);
}
__device__ __forceinline__ uint32_t ld_relaxed(const uint32_t* p) {
  uint32_t v; asm volatile("ld.relaxed.gpu.global.u32 %0, [%1];" : "=r"(v) : "l"(p) : "memory"); return v;
}
__device__ __forceinline__ uint32_t ld_acquire(const uint32_t* p) {
  uint32_t v; asm volatile("ld.acquire.gpu.global.u32 %0, [%1];" : "=r"(v) : "l"(p) : "memory"); return v;
}
__device__ __forceinline__ uint4 ld_relaxed4(const uint32_t* p) {
  uint4 v; asm volatile("ld.relaxed.gpu.global.v4.u32 {%0,%1,%2,%3}, [%4];" : "=r"(v.x), "=r"(v.y), "=r"(v.z), "=r"(v.w) : "l"(p) : "memory"); return v;
}
__device__ __forceinline__ uint2 ld_relaxed2(const uint32_t* p) {
  uint2 v; asm volatile("ld.relaxed.gpu.global.v2.u32 {%0,%1}, [%2];" : "=r"(v.x), "=r"(v.y) : "l"(p) : "memory"); return v;
}
__device__ __forceinline__ void st_relaxed(uint32_t* p, uint32_t v) {
  asm volatile("st.relaxed.gpu.global.u32 [%0], %1;" ::"l"(p), "r"(v) : "memory");
}
__device__ __forceinline__ void st_relaxed2(uint32_t* p, uint32_t a, uint32_t b) {
  asm volatile("st.relaxed.gpu.global.v2.u32 [%0], {%1,%2};" ::"l"(p), "r"(a), "r"(b) : "memory");
}
__device__ __forceinline__ void st_relaxed4(uint32_t* p, uint32_t a, uint32_t b, uint32_t c, uint32_t d) {
  asm volatile("st.relaxed.gpu.global.v4.u32 [%0], {%1,%2,%3,%4};" ::"l"(p), "r"(a), "r"(b), "r"(c), "r"(d) : "memory");
}
__device__ __forceinline__ void st_b128(uint32_t* p, uint32_t a, uint32_t b, uint32_t c, uint32_t d) {
  asm volatile("{ .reg .b64 u, v; .reg .b128 w; mov.b64 u, {%1, %2}; mov.b64 v, {%3, %4}; mov.b128 w, {u, v}; st.relaxed.gpu.global.b128 [%0], w; }"
               ::"l"(p), "r"(a), "r"(b), "r"(c), "r"(d) : "memory");
}
__device__ __forceinline__ uint4 ld_b128(const uint32_t* p) {
  uint4 r;
  asm volatile("{ .reg .b64 u, v; .reg .b128 w; ld.relaxed.gpu.global.b128 w, [%4]; mov.b128 {u, v}, w; mov.b64 {%0, %1}, u; mov.b64 {%2, %3}, v; }"
               : "=r"(r.x), "=r"(r.y), "=r"(r.z), "=r"(r.w) : "l"(p) : "memory");
  return r;
}
__device__ __forceinline__ void st_pairs(uint32_t* p, uint32_t a, uint32_t b, uint32_t tag) {
  asm volatile("{ .reg .b64 u, v; mov.b64 u, {%1, %3}; mov.b64 v, {%2, %3}; st.relaxed.gpu.global.v2.b64 [%0], {u, v}; }"
               ::"l"(p), "r"(a), "r"(b), "r"(tag) : "memory");
}
__device__ __forceinline__ uint4 ld_pairs(const uint32_t* p) {
  uint4 v;
  asm volatile("{ .reg .b64 u, v; ld.relaxed.gpu.global.v2.b64 {u, v}, [%4]; mov.b64 {%0, %1}, u; mov.b64 {%2, %3}, v; }"
               : "=r"(v.x), "=r"(v.y), "=r"(v.z), "=r"(v.w) : "l"(p) : "memory");
  return v;
}
__device__ __forceinline__ uint2 ld_pair(const uint32_t* p) {
  uint2 v;
  asm volatile("{ .reg .b64 u; ld.relaxed.gpu.global.b64 u, [%2]; mov.b64 {%0, %1}, u; }" : "=r"(v.x), "=r"(v.y) : "l"(p) : "memory");
  return v;
}
__device__ __forceinline__ void red_release(uint32_t* p, uint32_t v) {
  asm volatile("red.release.gpu.global.add.u32 [%0], %1;" ::"l"(p), "r"(v) : "memory");
}
__device__ __forceinline__ uint32_t ldg_nc1(const void* p) {
  uint32_t v;
  asm volatile("ld.global.nc.u32 %0, [%1];" : "=r"(v) : "l"(p));
  return v;
}
__device__ __forceinline__ uint4 ldg_nc4(const void* p) {
  uint4 v; asm volatile("ld.global.nc.L1::no_allocate.v4.u32 {%0,%1,%2,%3}, [%4];" : "=r"(v.x), "=r"(v.y), "=r"(v.z), "=r"(v.w) : "l"(p)); return v;
}
__device__ __forceinline__ uint4 ldg_stream4(const void* p) {
  uint4 v;
  asm volatile("ld.global.nc.L1::no_allocate.L2::cache_hint.v4.u32 {%0,%1,%2,%3}, [%4], %5;" : "=r"(v.x), "=r"(v.y), "=r"(v.z), "=r"(v.w) : "l"(p), "l"(l2_stream()));
  return v;
}
__device__ __forceinline__ void stg4(void* p, uint4 v) {
  asm volatile("st.global.v4.u32 [%0], {%1,%2,%3,%4};" ::"l"(p), "r"(v.x), "r"(v.y), "r"(v.z), "r"(v.w) : "memory");
}
__device__ __forceinline__ void wait_counter(const uint32_t* p, uint32_t target) {
  uint32_t n = 0;
  while (__any_sync(0xffffffffu, (int)(ld_acquire(p) - target) < 0)) { watchdog(n); }
}
__device__ __forceinline__ uint32_t tagf(float v, uint32_t tag) { return (__float_as_uint(v) & ~3u) | tag; }
__device__ __forceinline__ bool tag_ok(uint4 v, uint32_t tag) { return (((v.x ^ tag) | (v.y ^ tag) | (v.z ^ tag) | (v.w ^ tag)) & 3u) == 0; }
__device__ __forceinline__ float untag_sum(uint32_t a, uint32_t b) { return __uint_as_float(a & ~3u) + __uint_as_float(b & ~3u); }
__device__ __forceinline__ uint4 poll4(const uint32_t* p, uint32_t tag) {
  uint4 v = ld_relaxed4(p);
  uint32_t n = 0;
  while (!__all_sync(0xffffffffu, tag_ok(v, tag))) { v = ld_relaxed4(p); watchdog(n); }
  return v;
}
__device__ __forceinline__ float bf_lo(uint32_t v) { return __uint_as_float(v << 16); }
__device__ __forceinline__ float bf_hi(uint32_t v) { return __uint_as_float(v & 0xffff0000u); }
__device__ __forceinline__ uint32_t pack_bf(float lo, float hi) {
  uint32_t r; asm("cvt.rn.bf16x2.f32 %0, %1, %2;" : "=r"(r) : "f"(hi), "f"(lo)); return r;
}
__device__ __forceinline__ float rbf(float v) { return __uint_as_float(pack_bf(0.f, v) & 0xffff0000u); }
__device__ __forceinline__ uint32_t hmul2(uint32_t a, uint32_t b) {
  uint32_t r; asm("mul.rn.bf16x2 %0, %1, %2;" : "=r"(r) : "r"(a), "r"(b)); return r;
}
__device__ __forceinline__ uint32_t hadd2(uint32_t a, uint32_t b) {
  uint32_t r; asm("add.rn.bf16x2 %0, %1, %2;" : "=r"(r) : "r"(a), "r"(b)); return r;
}
__device__ __forceinline__ uint32_t hsub2(uint32_t a, uint32_t b) {
  uint32_t r; asm("sub.rn.bf16x2 %0, %1, %2;" : "=r"(r) : "r"(a), "r"(b)); return r;
}
__device__ __forceinline__ uint32_t hmax2(uint32_t a, uint32_t b) {
  uint32_t r; asm("max.bf16x2 %0, %1, %2;" : "=r"(r) : "r"(a), "r"(b)); return r;
}
__device__ __forceinline__ float rcp(float x) { float r; asm("rcp.approx.ftz.f32 %0, %1;" : "=f"(r) : "f"(x)); return r; }
__device__ __forceinline__ float ex2(float x) { float r; asm("ex2.approx.ftz.f32 %0, %1;" : "=f"(r) : "f"(x)); return r; }
__device__ __forceinline__ void stmatrix4(uint32_t addr, uint32_t a, uint32_t b, uint32_t c, uint32_t d) {
  asm volatile("stmatrix.sync.aligned.m8n8.x4.shared.b16 [%0], {%1,%2,%3,%4};" ::"r"(addr), "r"(a), "r"(b), "r"(c), "r"(d) : "memory");
}
__device__ __forceinline__ void ldmatrix4(uint32_t addr, uint32_t& a, uint32_t& b, uint32_t& c, uint32_t& d) {
  asm volatile("ldmatrix.sync.aligned.m8n8.x4.shared.b16 {%0,%1,%2,%3}, [%4];" : "=r"(a), "=r"(b), "=r"(c), "=r"(d) : "r"(addr) : "memory");
}
__device__ __forceinline__ void ldmatrix4t(uint32_t addr, uint32_t& a, uint32_t& b, uint32_t& c, uint32_t& d) {
  asm volatile("ldmatrix.sync.aligned.m8n8.x4.trans.shared.b16 {%0,%1,%2,%3}, [%4];" : "=r"(a), "=r"(b), "=r"(c), "=r"(d) : "r"(addr) : "memory");
}
__device__ __forceinline__ void mma16816(float (&d)[4], uint32_t a0, uint32_t a1, uint32_t a2, uint32_t a3, uint32_t b0, uint32_t b1) {
  asm volatile("mma.sync.aligned.m16n8k16.row.col.f32.bf16.bf16.f32 {%0,%1,%2,%3}, {%4,%5,%6,%7}, {%8,%9}, {%0,%1,%2,%3};"
               : "+f"(d[0]), "+f"(d[1]), "+f"(d[2]), "+f"(d[3]) : "r"(a0), "r"(a1), "r"(a2), "r"(a3), "r"(b0), "r"(b1));
}
__device__ __forceinline__ void sts1(uint32_t a, uint32_t v) { asm volatile("st.shared.u32 [%0], %1;" ::"r"(a), "r"(v) : "memory"); }
__device__ __forceinline__ uint4 lds4(uint32_t a) {
  uint4 v; asm volatile("ld.shared.v4.u32 {%0,%1,%2,%3}, [%4];" : "=r"(v.x), "=r"(v.y), "=r"(v.z), "=r"(v.w) : "r"(a) : "memory"); return v;
}
__device__ __forceinline__ uint2 lds2(uint32_t a) {
  uint2 v; asm volatile("ld.shared.v2.u32 {%0,%1}, [%2];" : "=r"(v.x), "=r"(v.y) : "r"(a) : "memory"); return v;
}
__device__ __forceinline__ uint32_t lds1(uint32_t a) {
  uint32_t v; asm volatile("ld.shared.u32 %0, [%1];" : "=r"(v) : "r"(a) : "memory"); return v;
}
__device__ __forceinline__ void sts2(uint32_t a, uint32_t x, uint32_t y) { asm volatile("st.shared.v2.u32 [%0], {%1,%2};" ::"r"(a), "r"(x), "r"(y) : "memory"); }
__device__ __forceinline__ void sts4(uint32_t a, uint4 v) {
  asm volatile("st.shared.v4.u32 [%0], {%1,%2,%3,%4};" ::"r"(a), "r"(v.x), "r"(v.y), "r"(v.z), "r"(v.w) : "memory");
}
__device__ __forceinline__ float silu_f(float v) { return __fdividef(v, 1.f + __expf(-v)); }
__device__ __forceinline__ uint32_t hfma2(uint32_t a, uint32_t b, uint32_t c) {
  uint32_t r; asm("fma.rn.bf16x2 %0, %1, %2, %3;" : "=r"(r) : "r"(a), "r"(b), "r"(c)); return r;
}
__device__ __forceinline__ void split_inv(float sd, uint32_t& ih, uint32_t& il) {
  const float inv = rcp(sd);
  ih = pack_bf(inv, inv);
  const float lo = inv - bf_lo(ih);
  il = pack_bf(lo, lo);
}
__device__ __forceinline__ uint32_t ln_norm(uint32_t x, uint32_t mean2, uint32_t ih, uint32_t il) {
  const uint32_t d = hsub2(x, mean2);
  return hfma2(d, ih, hmul2(d, il));
}
__device__ __forceinline__ uint32_t modul(uint32_t n, uint32_t c1, uint32_t sh) { return hadd2(hmul2(n, c1), sh); }
__device__ __forceinline__ uint32_t ln_mod(uint32_t x, uint32_t mean2, uint32_t ih, uint32_t il, uint32_t c1, uint32_t sh) {
  return modul(ln_norm(x, mean2, ih, il), c1, sh);
}

#define R8(a, i) "+f"(a[i]), "+f"(a[i + 1]), "+f"(a[i + 2]), "+f"(a[i + 3]), "+f"(a[i + 4]), "+f"(a[i + 5]), "+f"(a[i + 6]), "+f"(a[i + 7])
#define D64 "{%0,%1,%2,%3,%4,%5,%6,%7,%8,%9,%10,%11,%12,%13,%14,%15,%16,%17,%18,%19,%20,%21,%22,%23,%24,%25,%26,%27,%28,%29,%30,%31," \
            "%32,%33,%34,%35,%36,%37,%38,%39,%40,%41,%42,%43,%44,%45,%46,%47,%48,%49,%50,%51,%52,%53,%54,%55,%56,%57,%58,%59,%60,%61,%62,%63}"
template <int TB>
__device__ __forceinline__ void mma_ss(float (&d)[64], uint64_t da, uint64_t db, int sc) {
  asm volatile("{\n.reg .pred p;\nsetp.ne.b32 p, %66, 0;\n"
               "wgmma.mma_async.sync.aligned.m64n128k16.f32.bf16.bf16 " D64 ", %64, %65, p, 1, 1, 0, %67;\n}"
               : R8(d, 0), R8(d, 8), R8(d, 16), R8(d, 24), R8(d, 32), R8(d, 40), R8(d, 48), R8(d, 56)
               : "l"(da), "l"(db), "r"(sc), "n"(TB));
}
template <int TB>
__device__ __forceinline__ void mma_rs(float (&d)[64], uint32_t a0, uint32_t a1, uint32_t a2, uint32_t a3, uint64_t db, int sc) {
  asm volatile("{\n.reg .pred p;\nsetp.ne.b32 p, %69, 0;\n"
               "wgmma.mma_async.sync.aligned.m64n128k16.f32.bf16.bf16 " D64 ", {%64,%65,%66,%67}, %68, p, 1, 1, %70;\n}"
               : R8(d, 0), R8(d, 8), R8(d, 16), R8(d, 24), R8(d, 32), R8(d, 40), R8(d, 48), R8(d, 56)
               : "r"(a0), "r"(a1), "r"(a2), "r"(a3), "l"(db), "r"(sc), "n"(TB));
}
#define D128 "{%0,%1,%2,%3,%4,%5,%6,%7,%8,%9,%10,%11,%12,%13,%14,%15,%16,%17,%18,%19,%20,%21,%22,%23,%24,%25,%26,%27,%28,%29,%30,%31," \
             "%32,%33,%34,%35,%36,%37,%38,%39,%40,%41,%42,%43,%44,%45,%46,%47,%48,%49,%50,%51,%52,%53,%54,%55,%56,%57,%58,%59,%60,%61,%62,%63," \
             "%64,%65,%66,%67,%68,%69,%70,%71,%72,%73,%74,%75,%76,%77,%78,%79,%80,%81,%82,%83,%84,%85,%86,%87,%88,%89,%90,%91,%92,%93,%94,%95," \
             "%96,%97,%98,%99,%100,%101,%102,%103,%104,%105,%106,%107,%108,%109,%110,%111,%112,%113,%114,%115,%116,%117,%118,%119,%120,%121,%122,%123,%124,%125,%126,%127}"
#define R128(d, e) R8(d, 0), R8(d, 8), R8(d, 16), R8(d, 24), R8(d, 32), R8(d, 40), R8(d, 48), R8(d, 56), \
                   R8(e, 0), R8(e, 8), R8(e, 16), R8(e, 24), R8(e, 32), R8(e, 40), R8(e, 48), R8(e, 56)
__device__ __forceinline__ void mma256_ss(float (&d)[64], float (&e)[64], uint64_t da, uint64_t db, int sc) {
  asm volatile("{\n.reg .pred p;\nsetp.ne.b32 p, %130, 0;\n"
               "wgmma.mma_async.sync.aligned.m64n256k16.f32.bf16.bf16 " D128 ", %128, %129, p, 1, 1, 0, 1;\n}"
               : R128(d, e) : "l"(da), "l"(db), "r"(sc));
}
__device__ __forceinline__ void mma256_rs(float (&d)[64], float (&e)[64], uint32_t a0, uint32_t a1, uint32_t a2, uint32_t a3, uint64_t db) {
  asm volatile("{\n.reg .pred p;\nsetp.ne.b32 p, 1, 0;\n"
               "wgmma.mma_async.sync.aligned.m64n256k16.f32.bf16.bf16 " D128 ", {%128,%129,%130,%131}, %132, p, 1, 1, 1;\n}"
               : R128(d, e) : "r"(a0), "r"(a1), "r"(a2), "r"(a3), "l"(db));
}
template <int N> __device__ __forceinline__ void keep(float (&a)[N]) {
#pragma unroll
  for (int i = 0; i < N; i++) asm volatile("" : "+f"(a[i])::"memory");
}
template <int N> __device__ __forceinline__ void keep(uint32_t (&a)[N]) {
#pragma unroll
  for (int i = 0; i < N; i++) asm volatile("" : "+r"(a[i])::"memory");
}

#define STAMP(idx) do {} while (0)
#define PROF(grp, cond, idx) do {} while (0)

constexpr float SCL2 = 1.4426950408889634f * 0.08838834764831845f;

__device__ __forceinline__ void pack_p(const float (&s)[64], uint32_t (&p)[32]) {
#pragma unroll
  for (int i = 0; i < 32; i++) p[i] = pack_bf(s[2 * i], s[2 * i + 1]);
}

__device__ __forceinline__ void issue_qk(float (&s)[64], uint32_t q0, uint32_t q1, uint32_t kslot) {
  const uint64_t db = make_desc(kslot, 16, 1024), da0 = make_desc(q0, 16, 1024), da1 = make_desc(q1, 16, 1024);
#pragma unroll
  for (int kk = 0; kk < 8; kk++) mma_ss<0>(s, (kk < 4 ? da0 : da1) + (kk & 3) * 2, db + (kk >> 2) * 1024 + (kk & 3) * 2, kk != 0);
}
__device__ __forceinline__ void issue_pv(float (&o)[64], uint32_t (&p)[32], uint32_t vslot, int acc) {
  uint64_t db = make_desc(vslot, 16384, 1024);
#pragma unroll
  for (int kk = 0; kk < 8; kk++)
    mma_rs<1>(o, p[4 * kk], p[4 * kk + 1], p[4 * kk + 2], p[4 * kk + 3], db + kk * 128, kk == 0 ? acc : 1);
}

template <int H>
__device__ __forceinline__ void store_chunk(const float (&a)[64], uint32_t addr) {
#pragma unroll
  for (int i = 8 * H; i < 8 * H + 8; i += 2)
    stmatrix4(addr ^ ((i & 7) << 4), pack_bf(a[4 * i], a[4 * i + 1]), pack_bf(a[4 * i + 2], a[4 * i + 3]),
              pack_bf(a[4 * i + 4], a[4 * i + 5]), pack_bf(a[4 * i + 6], a[4 * i + 7]));
}
template <int H>
__device__ __forceinline__ void store_chunk(const float (&a)[64], float i0, float i1, uint32_t addr) {
#pragma unroll
  for (int i = 8 * H; i < 8 * H + 8; i += 2)
    stmatrix4(addr ^ ((i & 7) << 4), pack_bf(a[4 * i] * i0, a[4 * i + 1] * i0), pack_bf(a[4 * i + 2] * i1, a[4 * i + 3] * i1),
              pack_bf(a[4 * i + 4] * i0, a[4 * i + 5] * i0), pack_bf(a[4 * i + 6] * i1, a[4 * i + 7] * i1));
}
__device__ __forceinline__ float inv_quad_sum(float l) {
  l += __shfl_xor_sync(0xffffffffu, l, 1);
  l += __shfl_xor_sync(0xffffffffu, l, 2);
  return rcp(l);
}

__device__ __forceinline__ void write_table(uint32_t table, bool ca, uint32_t t, const uint4& m0, const uint4& m1) {
  float c0 = untag_sum(m0.x, m1.x), c1 = untag_sum(m0.y, m1.y), c2 = untag_sum(m0.z, m1.z), c3 = untag_sum(m0.w, m1.w);
  if (ca) { c0 = 1.f + rbf(c0); c1 = 1.f + rbf(c1); c2 = 1.f + rbf(c2); c3 = 1.f + rbf(c3); }
  const uint32_t d = table + (t >> 2) * 64 + (t & 1) * 32 + (t & 2) * 2 + (ca ? 0 : 8);
  sts1(d, pack_bf(c0, c1));
  sts1(d + 16, pack_bf(c2, c3));
}

__device__ __forceinline__ void ln_scalars(float mean, float var, float& mb, float& sd) {
  mb = rbf(mean);
  float r; asm("sqrt.approx.ftz.f32 %0, %1;" : "=f"(r) : "f"(rbf(rbf(var) + 1e-5f)));
  sd = rbf(r);
}

__global__ void __cluster_dims__(2, 1, 1) __launch_bounds__(384, 1) fused_kernel(const __grid_constant__ Maps maps, const Ptrs P) {
  extern __shared__ __align__(1024) uint8_t smem_raw[];
  const uint32_t base = smem_u32(smem_raw);
  const int tid = threadIdx.x, lane = tid & 31;
  const int warp = __shfl_sync(0xffffffffu, tid >> 5, 0);
  const int b = blockIdx.x;
  PROF(31, tid == 0, 0);

  if (b >= NMAIN) {
    float* sc = reinterpret_cast<float*>(smem_raw);
    float* red = sc + DM;
    for (int k = tid; k < DM; k += 384) sc[k] = rbf(silu_f(__bfloat162float(P.c[k])));
    __syncthreads();
    if (tid < 256) {
      const int col = 2048 + (b - NMAIN) * 1024 + (tid & 127) * 8, r0 = (tid >> 7) * 512;
      float acc[8];
#pragma unroll
      for (int e = 0; e < 8; e++) acc[e] = 0.f;
#pragma unroll 1
      for (int r = r0; r < r0 + 512; r += HU) {
        uint4 w[HU];
#pragma unroll
        for (int u = 0; u < HU; u++) w[u] = ldg_stream4(P.w_mod + (size_t)(r + u) * NMOD + col);
#pragma unroll
        for (int u = 0; u < HU; u++) {
          float s = sc[r + u];
          acc[0] += s * bf_lo(w[u].x); acc[1] += s * bf_hi(w[u].x); acc[2] += s * bf_lo(w[u].y); acc[3] += s * bf_hi(w[u].y);
          acc[4] += s * bf_lo(w[u].z); acc[5] += s * bf_hi(w[u].z); acc[6] += s * bf_lo(w[u].w); acc[7] += s * bf_hi(w[u].w);
        }
      }
      if (tid >= 128) {
#pragma unroll
        for (int e = 0; e < 8; e++) red[(tid & 127) * 8 + e] = acc[e];
      }
      const uint32_t tag = ld_relaxed(&g_epoch) % 3 + 1;
      bar_sync(1, 256);
      if (tid < 128) {
        uint32_t o[8];
#pragma unroll
        for (int e = 0; e < 8; e++) o[e] = __float_as_uint(rbf(acc[e] + red[tid * 8 + e])) | tag;
        st_relaxed4(g_mod + col, o[0], o[1], o[2], o[3]);
        st_relaxed4(g_mod + col + 4, o[4], o[5], o[6], o[7]);
        const uint4 wr = ldg_nc4(P.w_r + tid * 8);
        const uint32_t wv[4] = {wr.x, wr.y, wr.z, wr.w};
        float dsum = 0.f;
#pragma unroll
        for (int e = 0; e < 8; e++) {
          const float m = bf_hi(o[e]);
          dsum += (b == NMAIN + 2 ? rbf(1.f + m) : m) * ((e & 1) ? bf_hi(wv[e >> 1]) : bf_lo(wv[e >> 1]));
        }
#pragma unroll
        for (int k = 16; k > 0; k >>= 1) dsum += __shfl_xor_sync(0xffffffffu, dsum, k);
        if (lane == 0) st_relaxed(g_mod + (b - NMAIN) * 4 + warp, tagf(dsum, tag));
      }
    }
    PROF(2, tid == 0, 1);
    return;
  }

  const int rank = b & 1;
  const int rb = ((b >> 4) << 1) | rank, cj = (b >> 1) & 7;
  const bool late = b & 4;
  const uint32_t bfull = base + OFF_BAR, bempty = bfull + NSLOT * 8;
  const uint32_t gfull = bempty + NSLOT * 8, gempty = gfull + 32;
  const uint32_t bar_ofull = gempty + 32;
  const uint32_t bar_ofree = bar_ofull + 32;
  const uint32_t bar_par = bar_ofree + 32;
  const uint32_t bar_mod = bar_par + 8;
  const uint32_t bar_pread = bar_mod + 8;
  const uint32_t bar_xres = bar_pread + 8;
  const uint32_t bar_ring = bar_xres + 8;
  const uint32_t bar_box = bar_ring + 24;
  const uint32_t bar_go = bar_box + 96;
  const uint32_t bar_go2 = bar_go + 16;
  const uint32_t bar_cnt = bar_go + 24;
  const uint32_t xfull = bar_go + 40, xempty = xfull + 32;
  const uint32_t bar_hw = xempty + 32, bar_hx = bar_hw + 8;
  const uint32_t bar_hpub = bar_hx + 16;
  const uint32_t bar_win = bar_hpub + 16;
  const uint32_t bar_rx = bar_win + 8;
  const uint32_t bar_sel = bar_rx + 8;
  const uint32_t bar_gate = bar_sel + 8;
  const uint32_t bar_rel = bar_gate + 8;
  const uint32_t bar_od = bar_rel + 8;
  const uint32_t bar_mod2 = bar_od + 8;
  const uint32_t bar_res = bar_go + 8;
  const uint32_t stage = base + OFF_STAGE, par = base + OFF_PAR;

  if (warp == 10 && elect_one()) prefetch_map(&maps.wm);
  if (warp == 8 && elect_one()) {
    for (int s = 0; s < NSLOT; s++) { mbar_init(bfull + s * 8, 1); mbar_init(bempty + s * 8, 16); }
    for (int s = 0; s < 4; s++) { mbar_init(gfull + s * 8, 1); mbar_init(gempty + s * 8, 16); mbar_init(xfull + s * 8, 1); mbar_init(xempty + s * 8, 8); mbar_init(bar_ofree + s * 8, 1); mbar_init(bar_ofull + s * 8, 128); }
    mbar_init(bar_par, 64); mbar_init(bar_mod, 256); mbar_init(bar_pread, 2); mbar_init(bar_xres, 1);
    mbar_init(bar_ring, 8); mbar_init(bar_ring + 8, 8); mbar_init(bar_ring + 16, 8);
    mbar_init(bar_go, 1); mbar_init(bar_go2, 1); mbar_init(bar_cnt, 1); mbar_init(bar_cnt + 8, 1); mbar_init(bar_hpub, 8); mbar_init(bar_hpub + 8, 8); mbar_init(bar_res, 1); mbar_init(bar_win, 1); mbar_init(bar_rx, 1); mbar_init(bar_sel, 64); mbar_init(bar_gate, 8); mbar_init(bar_rel, 8); mbar_init(bar_od, 1); mbar_init(bar_mod2, 64);
    for (int s = 0; s < 12; s++) mbar_init(bar_box + s * 8, 1);
    asm volatile("fence.mbarrier_init.release.cluster;" ::: "memory");
    prefetch_map(&maps.x); prefetch_map(&maps.wq); prefetch_map(&maps.k); prefetch_map(&maps.v);
  }
  if (warp == 9 && elect_one()) {
    mbar_init(bar_hw, 1); mbar_init(bar_hx, 1); mbar_init(bar_hx + 8, 1);
    asm volatile("fence.mbarrier_init.release.cluster;" ::: "memory");
    mbar_expect_tx(bar_hw, 32768);
    mbar_expect_tx(bar_hx, 16384);
    mbar_expect_tx(bar_hx + 8, 16384);
    const __nv_bfloat16* xs = P.x + (size_t)(rb * 128 + cj * 16) * DM;
    bulk_load(base + 2 * GST_BYTES, xs, 16384, bar_hx);
    if (!late) {
      tma2d(stage, &maps.wm, (b >> 1) * 32, rank * 512, bar_hw);
      tma2d(stage + 16384, &maps.wm, (b >> 1) * 32, rank * 512 + 256, bar_hw);
    }
    bulk_load(base + 3 * GST_BYTES, xs + 8 * DM, 16384, bar_hx + 8);
  }
  cluster_arrive();

  if (warp >= 8) {
    asm volatile("setmaxnreg.dec.sync.aligned.u32 40;");
    if (warp < 10) bar_arrive(1, 320);
    const uint32_t epoch = ld_relaxed(&g_epoch);
    cluster_wait();
    if (warp == 8) {
      const int kvrow = (cj >> 1) * SK + (SK - WIN);
      int wch = cj * 8 + rank * 2;
#pragma unroll 1
      for (int ps = 0; ps < 3; ps++) {
        const CUtensorMap* mw = ps == 2 ? &maps.wo : &maps.wq;
        const uint32_t xt = ps == 1 ? XT1 : XT2, wt = ps == 0 ? WT0 : (ps == 1 ? WT1 : WT2);
        const int nst = ps == 2 ? 32 : 16;
#pragma unroll 1
        for (int i = 0; i < nst; i++) {
          const uint32_t bf = gfull + (i & 3) * 8;
          const int kt = ps == 2 ? (((cj & 1) * 4 + ((i >> 1) & 3)) * 4 + (i >> 3)) * 2 + (i & 1) : (ps ? i : slice_of(i) + (b & 14)) & 15;
          const uint32_t wd = base + unit_of(wt, i & 3) + rank * UNIT, xd = base + unit_of(xt, i & 3);
          const uint8_t* xs = g_act + (uint32_t)(rb * 80 + (ps - 1) * 16 + kt) * UNIT;
          if (ps == 0 && i == HD) mbar_wait(bar_mod, 0);
          const bool xfirst = ps && i < 2;
          if (ps == 2 && i == 0) mbar_wait(bar_ofree + 24, 0);
          if (i == 0) fence_async();
          mbar_wait(gempty + (i & 3) * 8, ((i >> 2) & 1) ^ 1);
          if (elect_one()) {
            mbar_expect_tx(bf, ps ? GST_BYTES : 2 * UNIT);
            if (xfirst) bulk_load_stream(xd, xs, UNIT, bf);
          }
          if (ps && i < 4) mbar_wait(bempty + i * 8, 1);
          if (elect_one()) tma3d_mc<true>(wd, mw, 0, (i == 31 ? kt ^ (rank * 32) : kt) * 64, i == 31 ? cj * 2 : wch, bf);
          if (ps) {
            if (i == 16 || i == 24) { mbar_wait(bar_cnt + i - 16, 0); fence_async(); }
            if (i == RES0) mbar_wait(bar_res, 0);
            if (i == 2) mbar_wait(bar_ofree + (ps - 1) * 16, 0);
            if (elect_one()) {
              if (i == 31) bulk_load(xd, xs, UNIT, bf); else if (!xfirst) bulk_load_stream(xd, xs, UNIT, bf);
              mbar_arrive_pred(bar_go, i == GOST - 1);
              if (PG0 < 16) mbar_arrive_pred(bar_go2, ps == 1 && i == PG0);
              mbar_arrive_pred(bar_od, i == (ps == 1 ? ODS1 : ODS));
              if (i == RES0) mbar_expect_tx(bar_xres, 32768);
              if (i == RES0 || i == RES1) tma2d(base + OFF_RES + (i == RES1) * UNIT, &maps.x, cj * 128 + (i == RES1) * 64, rb * 128, bar_xres);
            }
          }
        }
        if (ps == 2) break;
        wch = ps ? ((wch >> 3) ^ rank) * 2 : wch + 4;
#pragma unroll 1
        for (int u = 0; u < 16; u++) {
          const bool isk = (u == 0) || ((u & 1) && u < 15);
          const int blk = (isk ? (u + 1) >> 1 : (u == 15 ? 7 : (u >> 1) - 1)) & 3;
          const uint32_t sl = base + unit_of(ps ? AT1 : AT0, u & 3) + rank * UNIT, bf = bfull + (u & 3) * 8;
          if (u < 4) mbar_wait(gempty + ((u + 1) >> 1) * 8, 1);
          mbar_wait(bempty + (u & 3) * 8, ((u >> 2) & 1) ^ 1);
          if (elect_one()) {
            mbar_arrive_pred(bar_go2, ps && u + 16 == PG0);
            mbar_expect_tx(bf, SLOT_BYTES);
            tma3d_mc<false>(sl, isk ? &maps.k : &maps.v, 0, kvrow + blk * 128, rank, bf);
          }
        }
      }
      if (elect_one()) mbar_expect_tx(bar_rx, UNIT);
      mbar_wait(bar_rel, 0);
      if (elect_one()) {
        bulk_load_stream(base + UNIT, g_act + (uint32_t)(rb * 80 + 16 + 63 - (cj & 1) * 32) * UNIT, UNIT, bar_rx);
      }
      if (b < NFFN) {
#pragma unroll 1
        for (int u = 0; u < 12; u++) {
          const uint32_t dst = base + unit_of(u < 4 ? FT_G : (u < 8 ? FT_U : FT_D), u & 3);
          if (elect_one()) mbar_expect_tx(bar_box + u * 8, UNIT);
          if (u == FB0 || u == FB1 || u == FB2) mbar_wait(bar_ring + (u == FB2 ? 16 : u == FB1 ? 8 : 0), 0);
          const int fp = u < FPB ? FPACE0 : FPACE;
          if (u >= fp) mbar_wait(bar_box + (u - fp) * 8, 0);
          if (elect_one()) {
            if (u < 8) tma2d(dst, u < 4 ? &maps.wg : &maps.wu, b * 32, (u & 3) * 256, bar_box + u * 8);
            else tma3d(dst, &maps.wd, 0, b * 32, (u - 8) * 4, bar_box + u * 8);
          }
        }
      }
    } else if (warp == 9) {
      const uint32_t target = 8 * (epoch + 1);
      uint32_t hmask = 0;
#pragma unroll 1
      for (int i = 0; i < 16; i++) {
        if (i == HDX) mbar_wait(bar_mod, 0);
        const int kt = (2 * cj + slice_of(i)) & 15;
        const uint32_t need = i == 15 ? 0xffffu : 1u << kt;
        if (i >= NRS && (hmask & need) != need) {
          uint32_t n = 0;
          do { hmask = __ballot_sync(0xffffffffu, ld_acquire(&g_cnt_h[rb * 32 + (lane & 15)]) == epoch + 1); watchdog(n); } while ((hmask & need) != need);
          PROF(1, lane == 0 && i == NRS, 26);
          fence_async();
        }
        mbar_wait(xempty + (i & 3) * 8, ((i >> 2) & 1) ^ 1);
        if (elect_one()) {
          mbar_expect_tx(xfull + (i & 3) * 8, UNIT);
          if (i < NRS) tma2d(base + (i & 3) * GST_BYTES, &maps.x, kt * 64, rb * 128, xfull + (i & 3) * 8);
          else bulk_load_stream(base + (i & 3) * GST_BYTES, g_act + (uint32_t)(rb * 80 + kt) * UNIT, UNIT, xfull + (i & 3) * 8);
        }
      }
      prefetch_map(&maps.wo);
#pragma unroll 1
      for (int t = 0; t < 4; t++) {
        if (t & 1) mbar_wait(bar_od, t >> 1);
#pragma unroll 1
        for (int p = 0; p < 32768 / OPS; p++) {
          const uint32_t w = p / (16384 / OPS), c = (p / (8192 / OPS)) & 1, off = w * 8192 + (p % (8192 / OPS)) * OPS;
          mbar_wait(bar_ofull + (t & 1) * 16 + w * 8, t >> 1);
          if (elect_one()) {
            bulk_store(g_act + (uint32_t)(rb * 80 + 16 + (cj * 4 + t) * 2 + c) * UNIT + off, base + unit_of(QT, 2 * t + c) + off, OPS);
            asm volatile("cp.async.bulk.commit_group;" ::: "memory");
            asm volatile("cp.async.bulk.wait_group.read %0;" ::"n"(OFL) : "memory");
          }
        }
        if (elect_one()) {
          asm volatile("cp.async.bulk.wait_group.read 0;" ::: "memory");
          mbar_arrive(t < 3 ? bar_ofree + t * 8 : bar_res);
          asm volatile("cp.async.bulk.wait_group 0;" ::: "memory");
          fence_async();
          red_release(&g_cnt_o[((rb * 4 + t) * 2 + (cj >> 2)) * 32], 2);
        }
        if (t) {
          wait_counter(&g_cnt_o[(rb * 8 + 2 * t + (cj & 1)) * 32], target);
          if (t & 1) wait_counter(&g_cnt_o[(rb * 8 + (t == 1 ? cj & 1 : 7 - (cj & 1))) * 32], target);
          if (elect_one()) mbar_arrive(t == 1 ? bar_ofree + 24 : bar_cnt + t * 8 - 16);
        }
      }
      PROF(2, lane == 0, 27);
      const uint32_t tag = epoch % 3 + 1;
      const uint32_t* inbox = g_cand + (lane & 15);
      mbar_wait(bar_ring + 16, 0);
      uint32_t c0 = ld_relaxed(inbox), n = 0;
#define CAND_STEP(cv)                                                                                        \
      {                                                                                                      \
        const bool valid = (cv & 3u) == tag, all = __all_sync(0xffffffffu, valid);                           \
        const uint32_t best = __reduce_max_sync(0xffffffffu, valid ? cv : 0u);                               \
        const uint32_t blk = __ffs(__ballot_sync(0xffffffffu, cv == best)) - 1;                              \
        if (best) sts2(par + PAR_CONST + 56, best, (blk << 7 | (~best >> 2 & 127)) | (all ? 0x1800 : 0x800)); \
        if (all) break;                                                                                      \
        cv = ld_relaxed(inbox);                                                                              \
      }
      while (true) { CAND_STEP(c0) watchdog(n); }
    } else {
      const int t2 = tid - 320;
      if (late && warp == 10) {
        mbar_wait(bar_hx, 0);
        if (elect_one()) {
          tma2d(stage, &maps.wm, (b >> 1) * 32, rank * 512, bar_hw);
          tma2d(stage + 16384, &maps.wm, (b >> 1) * 32, rank * 512 + 256, bar_hw);
        }
      }
      {
        const uint32_t tag = epoch % 3 + 1;
        mbar_wait(bar_hx + 8, 0);
        mbar_wait(bar_hw, 0);
        __nanosleep(late ? OSL2 : OSL);
        {
          const uint32_t t7 = (warp & 1) * 64 + (lane >> 4) * 32 + 16 + (lane & 15);
          const uint32_t* pm = g_modp + ((cj * 128 + t7 * 4) & (DM - 1));
          uint4 m0, m1, m2, m3;
          uint32_t n = 0;
          do {
            m0 = ld_relaxed4(pm); m1 = ld_relaxed4(pm + 2 * DM); m2 = ld_relaxed4(pm + DM); m3 = ld_relaxed4(pm + 3 * DM);
            watchdog(n);
          } while (!__all_sync(0xffffffffu, tag_ok(m0, tag) && tag_ok(m1, tag) && tag_ok(m2, tag) && tag_ok(m3, tag)));
          write_table(par, false, t7, m0, m1);
          write_table(par, true, t7, m2, m3);
          mbar_arrive(bar_mod2);
        }
      }
      mbar_wait(bar_hpub + (warp & 1) * 8, 0);
      PROF(1, t2 == 0, 24);
#pragma unroll 1
      for (int c = 0; c < 8; c++) {
        const uint32_t off = (warp & 1) * UNIT + c * 2048 + lane * 16;
        uint8_t* dst = g_act + (uint32_t)(rb * 80 + cj * 2) * UNIT + off;
        const uint4 v0 = lds4(stage + off), v1 = lds4(stage + off + 512), v2 = lds4(stage + off + 1024), v3 = lds4(stage + off + 1536);
        stg4(dst, v0); stg4(dst + 512, v1); stg4(dst + 1024, v2); stg4(dst + 1536, v3);
      }
      __syncwarp();
      PROF(1, t2 == 0, 15);
      if (lane == 0) {
        mbar_arrive(bar_pread);
        red_release(&g_cnt_h[rb * 32 + cj * 2 + (warp & 1)], 1);
        PROF(1, t2 == 0, 25);
        prefetch_map(&maps.wg); prefetch_map(&maps.wu); prefetch_map(&maps.wd); prefetch_map(&maps.out);
      }
      __syncwarp();
      if (b < NFFN) {
        mbar_wait(bar_go2, 0);
        const __nv_bfloat16* pg = ((b & 1) ? P.w_up : P.w_gate) + (b >> 1) * 64 + (size_t)t2 * FF;
        const __nv_bfloat16* pd = P.w_down + (size_t)b * 32768 + t2 * 64;
        PROF(2, t2 == 0, 13);
#pragma unroll 1
        for (int i = 0; i < WN; i += WB) {
          uint32_t v[WB];
#pragma unroll
          for (int u = 0; u < WB; u++) {
            const int k = i + u;
            asm volatile("ld.global.cg.L2::128B.u32 %0, [%1];" : "=r"(v[u]) : "l"(k < 16 ? pg + (size_t)k * 64 * FF : pd + (k - 16) * 4096));
          }
#pragma unroll
          for (int u = 1; u < WB; u++) v[0] ^= v[u];
          sts1(par + PAR_SINK + t2 * 4, v[0]);
        }
        PROF(2, t2 == 0, 14);
      }
      const uint32_t tag = epoch % 3 + 1;
      mbar_wait(bar_go, 0);
      bar_sync(4, 64);
      if (warp == 10) {
        const uint32_t* src = g_mod + 2 * DM + cj * 128 + lane * 4;
        const uint2 wr = *reinterpret_cast<const uint2*>(P.w_r + cj * 128 + lane * 4);
        uint4 vga, vsb, vcb, vgb;
        uint32_t n = 0;
        do {
          vga = ld_relaxed4(src); vsb = ld_relaxed4(src + DM); vcb = ld_relaxed4(src + 2 * DM); vgb = ld_relaxed4(src + 3 * DM);
          watchdog(n);
        } while (!__all_sync(0xffffffffu, tag_ok(vga, tag) && tag_ok(vsb, tag) && tag_ok(vcb, tag) && tag_ok(vgb, tag)));
        const float c0 = rbf(1.f + bf_hi(vcb.x)), c1 = rbf(1.f + bf_hi(vcb.y)), c2 = rbf(1.f + bf_hi(vcb.z)), c3 = rbf(1.f + bf_hi(vcb.w));
        const float a0 = c0 * bf_lo(wr.x), a1 = c1 * bf_hi(wr.x), a2 = c2 * bf_lo(wr.y), a3 = c3 * bf_hi(wr.y);
        const uint32_t h0 = pack_bf(a0, a1), h1 = pack_bf(a2, a3);
        const uint32_t t1 = par + PAR_T1 + (lane >> 2) * 64 + (lane & 1) * 32 + (lane & 2) * 2;
        sts1(t1, h0); sts1(t1 + 8, pack_bf(a0 - bf_lo(h0), a1 - bf_hi(h0)));
        sts1(t1 + 16, h1); sts1(t1 + 24, pack_bf(a2 - bf_lo(h1), a3 - bf_hi(h1)));
        const uint32_t tg = par + PAR_SINK + (lane >> 3) * 64 + (lane & 1) * 32 + (lane & 6) * 2;
        sts1(tg, __byte_perm(vga.x, vga.y, 0x7632)); sts1(tg + 16, __byte_perm(vga.z, vga.w, 0x7632));
        sts4(par + PAR_T2 + lane * 32, make_uint4(pack_bf(c0, c1), __byte_perm(vsb.x, vsb.y, 0x7632), __byte_perm(vgb.x, vgb.y, 0x7632), __byte_perm(vga.x, vga.y, 0x7632)));
        sts4(par + PAR_T2 + lane * 32 + 16, make_uint4(pack_bf(c2, c3), __byte_perm(vsb.z, vsb.w, 0x7632), __byte_perm(vgb.z, vgb.w, 0x7632), __byte_perm(vga.z, vga.w, 0x7632)));
      } else {
        const uint4 g = poll4((lane & 2) ? g_mod + 8 - (lane & 1) * 4 : g_mod + 5 * DM + b * 8 + (lane & 1) * 4, tag);
        sts1(par + PAR_CONST + 60, 0);
        if (lane < 2) sts4(par + PAR_CONST + 16 + lane * 16, g);
        else if (lane < 4) sts2(par + PAR_CONST + (lane - 2) * 8, __float_as_uint(untag_sum(g.x, g.y) + untag_sum(g.z, g.w)), epoch);
      }
      __syncwarp();
#pragma unroll 4
      for (int q = 0; q < 32; q++) st_b128(g_xch + ((size_t)b * 8 * 256 + q * 64 + t2) * 4, (epoch & 1) << 16, 0, 0, 0);
      for (int q = 0; q < 2; q++) st_relaxed4(g_stats + ((size_t)cj * SEQ + rb * 128 + q * 64 + t2) * 4, 0, 0, 0, 0);
      if (b < NFFN)
        for (int q = 0; q < 4; q++) st_relaxed4(g_ypart + ((size_t)(q * 32 + (t2 >> 1)) * NFFN + b) * 8 + (t2 & 1) * 4, 0, 0, 0, 0);
      st_relaxed4(g_row + rb * 2 * DM + (t2 >> 5) * DM + cj * 128 + (t2 & 31) * 4, 0, 0, 0, 0);
      __threadfence();
      mbar_arrive(bar_par);
      mbar_wait(bar_gate, 0);
      uint32_t have = 0, n = 0;
      while (true) {
        const uint32_t st = lds1(par + PAR_CONST + 60) >> 7;
        if ((st & 31) != have) {
          const uint32_t* hsrc = g_row + (st & 15) * 2 * DM + t2 * 4;
          uint4 hv[4];
          bool ok = true;
#pragma unroll
          for (int i = 0; i < 4; i++) hv[i] = ld_pairs(hsrc + i * 256);
#pragma unroll
          for (int i = 0; i < 4; i++) {
            sts2(base + ((FT_G >> i * 4) & 15) * UNIT + (warp & 1) * 8192 + 256 + lane * 8, hv[i].x, hv[i].z);
            ok = ok && hv[i].y == tag && hv[i].w == tag;
          }
          have = __all_sync(0xffffffffu, ok) ? st & 31 : 0;
        }
        if ((st ^ have) == 32) break;
        watchdog(n);
      }
      mbar_arrive(bar_sel);
    }
    __syncwarp();
    cluster_arrive();
    {
      const uint32_t tag = epoch % 3 + 1, t3 = tid - 256;
      mbar_wait(bar_win, 0);
      uint2 win = lds2(par + PAR_CONST + 56);
      win.y &= 0x7ff;
      const uint32_t* fsrc = g_row + (win.y >> 7) * 2 * DM + (b >> 1) * 16 + (t3 & 3) * 4 + (b & 1) * 2;
      const uint32_t* ysrc = g_ypart + (size_t)b * NFFN * 8 + min(t3, NFFN - 1) * 4;
      uint2 fh = ld_pair(fsrc), fx = ld_pair(fsrc + DM);
      if (PSL) __nanosleep(PSL);
      uint4 ya = ld_relaxed4(ysrc), yb = ld_relaxed4(ysrc + NFFN * 4);
      const float rwin = __uint_as_float(((int)win.x < 0 ? win.x & 0x7fffffffu : ~win.x) & ~0x1ffu);
      const float rs = rbf(rcp(1.f + __expf(-rbf(rwin))));
      uint32_t n = 0;
      while (__any_sync(0xffffffffu, fh.y != tag || fx.y != tag)) { fh = ld_pair(fsrc); fx = ld_pair(fsrc + DM); watchdog(n); }
      while (!__all_sync(0xffffffffu, tag_ok(ya, tag) && tag_ok(yb, tag))) {
        if (!tag_ok(ya, tag)) ya = ld_relaxed4(ysrc);
        if (!tag_ok(yb, tag)) yb = ld_relaxed4(ysrc + NFFN * 4);
        watchdog(n);
      }
      __syncwarp();
      PROF(8, t3 == 0, 5);
      float y0 = untag_sum(ya.x, yb.x), y1 = untag_sum(ya.y, yb.y), y2 = untag_sum(ya.z, yb.z), y3 = untag_sum(ya.w, yb.w);
      const bool u1 = lane & 2, u2 = lane & 4;
      y0 = (u1 ? y2 : y0) + __shfl_xor_sync(0xffffffffu, u1 ? y0 : y2, 2);
      y1 = (u1 ? y3 : y1) + __shfl_xor_sync(0xffffffffu, u1 ? y1 : y3, 2);
      y0 = (u2 ? y1 : y0) + __shfl_xor_sync(0xffffffffu, u2 ? y0 : y1, 4);
      y0 += __shfl_xor_sync(0xffffffffu, y0, 8);
      if (!(lane & 8)) sts1(par + PAR_RED + 64 + (t3 >> 4) * 32 + ((lane & 1) * 4 + (lane & 2) + ((lane >> 2) & 1)) * 4, __float_as_uint(y0));
      bar_sync(4, 128);
      if (t3 < 4) {
        y0 = 0.f; y1 = 0.f;
#pragma unroll
        for (int w4 = 0; w4 < 7; w4++) {
          const uint2 v = lds2(par + PAR_RED + 64 + w4 * 32 + t3 * 8);
          y0 += __uint_as_float(v.x); y1 += __uint_as_float(v.y);
        }
        const uint2 gv = lds2(par + PAR_CONST + 16 + t3 * 8);
        const uint32_t upd = hmul2(pack_bf(y0, y1), pack_bf(rs, rs));
        *reinterpret_cast<uint32_t*>(P.out + (size_t)win.y * DM + b * 8 + t3 * 2) =
            hadd2(fx.x, hmul2(__byte_perm(gv.x, gv.y, 0x7632), hadd2(fh.x, upd)));
        if (b == 0 && t3 == 0) st_relaxed(&g_epoch, epoch + 1);
      }
      PROF(31, t3 == 0, 36);
    }
    cluster_wait();
  } else {
    const int wg = warp >> 2;

    uint32_t tag;
    {
      uint32_t* const pmod = g_modp + rank * 2 * DM + (b >> 1) * 32 + lane;
      uint32_t* const pln = g_ln1 + (rb * 128 + cj * 16 + warp) * 4;
      uint32_t sc[8];
#pragma unroll
      for (int k = 0; k < 8; k++) sc[k] = ldg_nc1(P.c + rank * 512 + warp * 64 + k * 8 + (lane & 3) * 2);
      const uint32_t epoch = ld_relaxed(&g_epoch);
      if (warp == 0) st_relaxed(pmod, 0);
      if (lane == 0) { st_b128(pln, 0, 0, 0, 0); st_b128(pln + 32, 0, 0, 0, 0); }
      asm volatile("setmaxnreg.inc.sync.aligned.u32 232;");
      bar_sync(1, 320);
#pragma unroll
      for (int k = 0; k < 8; k++) sc[k] = pack_bf(silu_f(bf_lo(sc[k])), silu_f(bf_hi(sc[k])));
      keep(sc);
      tag = epoch % 3 + 1;
#pragma unroll
      for (int part = 0; part < 4; part++) {
        if (!(part & 1)) {
          const uint32_t xa = base + (2 + part / 2) * GST_BYTES + warp * 2048 + lane * 16;
          mbar_wait(bar_hx + part * 4, 0);
          float s0 = 0.f, s1 = 0.f, q0 = 0.f, q1 = 0.f;
#pragma unroll
          for (int q = 0; q < 4; q++) {
            const uint4 xv = lds4(xa + q * 512);
            const uint32_t u[4] = {xv.x, xv.y, xv.z, xv.w};
#pragma unroll
            for (int e = 0; e < 4; e++) { const float lo = bf_lo(u[e]), hi = bf_hi(u[e]); s0 += lo; s1 += hi; q0 += lo * lo; q1 += hi * hi; }
          }
          s0 += s1; q0 += q1;
#pragma unroll
          for (int o = 16; o > 0; o >>= 1) { s0 += __shfl_xor_sync(0xffffffffu, s0, o); q0 += __shfl_xor_sync(0xffffffffu, q0, o); }
          const float mean = s0 * (1.f / DM);
          float mb, sd;
          ln_scalars(mean, fmaxf(q0 * (1.f / DM) - mean * mean, 0.f), mb, sd);
          uint32_t ih, il;
          split_inv(sd, ih, il);
          if (lane == 0) st_b128(pln + part * 16, pack_bf(mb, mb), ih, il, tag);
          PROF(1, tid == 0 && part == 2, 4);
        } else if (late == (part == 3)) {
          const uint32_t fr = (lane & 7) + (lane >> 4) * 8, tq = lane & 3;
          const uint32_t wa = stage + warp * 4096 + fr * 64 + ((((lane >> 3) & 1) ^ ((fr >> 1) & 3)) << 4);
          float d0[4] = {0.f, 0.f, 0.f, 0.f}, d1[4] = {0.f, 0.f, 0.f, 0.f};
          mbar_wait(bar_hw, 0);
#pragma unroll
          for (int ks = 0; ks < 4; ks++) {
            uint32_t w[8];
            ldmatrix4t(wa + ks * 1024, w[0], w[1], w[2], w[3]);
            ldmatrix4t((wa ^ 32) + ks * 1024, w[4], w[5], w[6], w[7]);
            mma16816(d0, w[0], w[1], w[2], w[3], sc[2 * ks], sc[2 * ks + 1]);
            mma16816(d1, w[4], w[5], w[6], w[7], sc[2 * ks], sc[2 * ks + 1]);
          }
          sts1(base + 2 * GST_BYTES + warp * 2048 + (tq * 8 + (lane >> 2)) * 4, __float_as_uint((tq & 2) ? ((tq & 1) ? d1[2] : d1[0]) : ((tq & 1) ? d0[2] : d0[0])));
          bar_sync(1, 256);
          if (warp == 0) {
            float s = 0.f;
#pragma unroll
            for (int w8 = 0; w8 < 8; w8++) s += __uint_as_float(lds1(base + 2 * GST_BYTES + w8 * 2048 + lane * 4));
            st_relaxed(pmod, (__float_as_uint(s) & ~3u) | tag);
          }
          PROF(1, tid == 0, 3);
        }
      }
      cluster_wait();
      if (wg == 1) bar_arrive(2, 256);
    }

    float f0 = 0.f, f1 = 0.f;
    const uint32_t rempty = lane < 2 ? mapa(bempty, lane & 1) : 0;
    constexpr uint32_t GE = NSLOT * 8 + 32;
    float o[64], s[64];
#pragma unroll 1
    for (int ps = 0; ps < 3; ps++) {
      {
        const uint32_t xt = ps == 1 ? XT1 : XT2, wt = ps == 1 ? WT1 : WT2;
        const int nst = ps == 2 ? 28 : 14;
        if (ps == 0) {
          float ga[64], gb[64];
#pragma unroll
          for (int i = 0; i < 64; i++) { ga[i] = 0.f; gb[i] = 0.f; }
          uint32_t a[2][16];
          const uint32_t l = fresh_lane();
          uint32_t fa[4];
#pragma unroll
          for (int kk = 0; kk < 4; kk++) fa[kk] = (base + wg * 8192 + frag_offset(warp)) ^ (kk * 32);
          const uint32_t mt = par + (l & 3) * 16;
          auto fetch = [&](int i, uint32_t (&f)[16], uint32_t z) {
            mbar_wait(xfull + (i & 3) * 8, i >> 2);
#pragma unroll
            for (int kk = 0; kk < 4; kk++) ldmatrix4(fa[kk] + (i & 3) * GST_BYTES + z, f[4 * kk], f[4 * kk + 1], f[4 * kk + 2], f[4 * kk + 3]);
          };
          const bool oddw = warp & 2;
          uint4 r0, r1;
          {
            const uint32_t t7 = (warp & 1) * 64 + (l >> 4) * 32 + (l & 15);
            const uint32_t* pm = g_modp + wg * DM + ((cj * 128 + t7 * 4) & (DM - 1));
            const uint32_t* pr = g_ln1 + (rb * 128 + warp * 16 + (l >> 2)) * 4;
            uint4 m0 = make_uint4(tag, tag, tag, tag), m1 = m0;
            if (!oddw) { m0 = ld_relaxed4(pm); m1 = ld_relaxed4(pm + 2 * DM); }
            r0 = ld_b128(pr); r1 = ld_b128(pr + 32);
            fetch(0, a[0], 0); fetch(1, a[1], 0);
            uint32_t n = 0;
            bool written = false;
#pragma unroll 1
            while (true) {
              uint32_t miss;
              asm volatile("{ .reg .pred p0, p1, p2, p3; .reg .b32 t, u;\n"
                           "lop3.b32 t, %1, %2, %19, 0x7e; lop3.b32 u, %3, %4, %19, 0x7e; or.b32 t, t, u; and.b32 t, t, 3; setp.ne.u32 p0, t, 0;\n"
                           "lop3.b32 t, %5, %6, %19, 0x7e; lop3.b32 u, %7, %8, %19, 0x7e; or.b32 t, t, u; and.b32 t, t, 3; setp.ne.u32 p1, t, 0;\n"
                           "setp.ne.u32 p2, %12, %19; setp.ne.u32 p3, %16, %19;\n"
                           "@p0 ld.relaxed.gpu.global.v4.u32 {%1, %2, %3, %4}, [%17];\n"
                           "@p1 ld.relaxed.gpu.global.v4.u32 {%5, %6, %7, %8}, [%17 + 8192];\n"
                           "@p2 ld.relaxed.gpu.global.v4.u32 {%9, %10, %11, %12}, [%18];\n"
                           "@p3 ld.relaxed.gpu.global.v4.u32 {%13, %14, %15, %16}, [%18 + 128];\n"
                           "or.pred p0, p0, p1; or.pred p2, p2, p3; vote.sync.any.pred p0, p0, 0xffffffff; vote.sync.any.pred p2, p2, 0xffffffff;\n"
                           "selp.u32 t, 1, 0, p0; selp.u32 u, 2, 0, p2; or.b32 %0, t, u; }"
                           : "=r"(miss), "+r"(m0.x), "+r"(m0.y), "+r"(m0.z), "+r"(m0.w), "+r"(m1.x), "+r"(m1.y), "+r"(m1.z), "+r"(m1.w),
                             "+r"(r0.x), "+r"(r0.y), "+r"(r0.z), "+r"(r0.w), "+r"(r1.x), "+r"(r1.y), "+r"(r1.z), "+r"(r1.w)
                           : "l"(pm), "l"(pr), "r"(tag) : "memory");
              if (!(miss & 1) && !written) {
                written = true;
                if (!oddw) write_table(par, wg, t7, m0, m1);
                mbar_arrive(bar_mod);
              }
              if (!miss) break;
              watchdog(n);
            }
          }
          const uint32_t zero = r0.w ^ tag;
          auto normalize = [&](uint32_t (&f)[16]) {
#pragma unroll
            for (int k = 0; k < 16; k += 2) { f[k] = ln_norm(f[k], r0.x, r0.y, r0.z); f[k + 1] = ln_norm(f[k + 1], r1.x, r1.y, r1.z); }
          };
          auto modulate = [&](int i, uint32_t (&f)[16]) {
#pragma unroll
            for (int kk = 0; kk < 4; kk++) {
              const uint4 m = lds4(mt + slice_of(i) * 256 + kk * 64);
              f[4 * kk] = MODUL(f[4 * kk], m.x, m.z); f[4 * kk + 1] = MODUL(f[4 * kk + 1], m.x, m.z);
              f[4 * kk + 2] = MODUL(f[4 * kk + 2], m.y, m.w); f[4 * kk + 3] = MODUL(f[4 * kk + 3], m.y, m.w);
            }
            keep(f);
            mbar_arrive_pred(xempty + (i & 3) * 8, l == 0);
          };
          auto publish = [&](int u, uint32_t (&f)[16]) {
#pragma unroll
            for (int kk = 0; kk < 4; kk++) stmatrix4(fa[kk] + OFF_STAGE + u * UNIT, f[4 * kk], f[4 * kk + 1], f[4 * kk + 2], f[4 * kk + 3]);
            __syncwarp();
            mbar_arrive_pred(bar_hpub + u * 8, l == 0);
          };
          auto multiply = [&](int i, uint32_t (&f)[16]) {
            mbar_wait(gfull + (i & 3) * 8, i >> 2);
            const uint64_t db = make_desc(base + (i & 3) * GST_BYTES + UNIT, 8192, 1024);
            wg_fence();
#pragma unroll
            for (int kk = 0; kk < 4; kk++) mma256_rs(ga, gb, f[4 * kk], f[4 * kk + 1], f[4 * kk + 2], f[4 * kk + 3], db + kk * 128);
            wg_commit();
          };
          auto next = [&](int i, uint32_t (&f)[16]) {
            wg_wait<1>();
            mbar_arrive_cl(rempty, GE + ((i + 2) & 3) * 8);
            uint32_t z = zero;
#pragma unroll
            for (int k = 0; k < 16; k += 2) asm volatile("lop3.b32 %0, %1, %2, %0, 0xA8;" : "+r"(z) : "r"(f[k]), "r"(f[k + 1]));
            fetch(i, f, z);
            normalize(f);
            if (i == 2) { keep(f); mbar_wait(bar_mod2, 0); }
            modulate(i, f); multiply(i, f);
          };
          normalize(a[0]); normalize(a[1]);
          keep(a[0]); keep(a[1]);
          mbar_wait(bar_mod, 0);
          PROF(1, tid == 0, 2);
          modulate(0, a[0]); multiply(0, a[0]); publish(0, a[0]);
          modulate(1, a[1]); multiply(1, a[1]);
#pragma unroll 1
          for (int i = 2; i < NRS; i += 2) {
            next(i, a[0]);
            if (i == 2) publish(1, a[0]);
            next(i + 1, a[1]);
          }
          wg_wait<1>();
          mbar_arrive_cl(rempty, GE + ((NRS + 2) & 3) * 8);
#pragma unroll 1
          for (int i = NRS; i < 14; i++) {
            mbar_wait(xfull + (i & 3) * 8, (i >> 2) & 1);
            mbar_wait(gfull + (i & 3) * 8, (i >> 2) & 1);
            const uint32_t xa = base + (i & 3) * GST_BYTES;
            const uint64_t da = make_desc(xa + wg * 8192, 16, 1024), db = make_desc(xa + UNIT, 8192, 1024);
            if (i == 13) bar_sync(2 + wg, 256);
            wg_fence();
#pragma unroll
            for (int kk = 0; kk < 4; kk++) mma256_ss(ga, gb, da + kk * 2, db + kk * 128, 1);
            wg_commit();
            if (i == 13) bar_arrive(3 - wg, 256);
            wg_wait<1>();
            uint32_t z = zero;
#pragma unroll
            for (int k = 0; k < 16; k += 2) asm volatile("lop3.b32 %0, %1, %2, %0, 0xA8;" : "+r"(z) : "r"(a[1][k]), "r"(a[1][k + 1]));
            mbar_arrive_cl(rempty, GE + ((i + 3) & 3) * 8 + z);
            mbar_arrive_pred(xempty + ((i + 3) & 3) * 8, l == 0 && i != NRS);
          }
          mbar_wait(xfull + 16, 1);
          wg_wait<0>();
          keep(ga); keep(gb);
#pragma unroll
          for (int i = 0; i < 64; i++) {
            asm volatile("mov.b32 %0, %1;" : "=f"(s[i]) : "f"(ga[i]));
            asm volatile("mov.b32 %0, %1;" : "=f"(o[i]) : "f"(gb[i]));
          }
        } else {
          float ga[64], gb[64];
#pragma unroll
          for (int i = 0; i < 64; i++) {
            asm volatile("mov.b32 %0, %1;" : "=f"(ga[i]) : "f"(s[i]));
            asm volatile("mov.b32 %0, %1;" : "=f"(gb[i]) : "f"(o[i]));
          }
#pragma unroll 1
          for (int i = 0; i < nst; i++) {
            mbar_wait(gfull + (i & 3) * 8, (i >> 2) & 1);
            const uint64_t da = make_desc(base + unit_of(xt, i & 3) + wg * 8192, 16, 1024), db = make_desc(base + unit_of(wt, i & 3), 8192, 1024);
            if (i == nst - 1) bar_sync(2 + wg, 256);
            wg_fence();
#pragma unroll
            for (int kk = 0; kk < 4; kk++) mma256_ss(ga, gb, da + kk * 2, db + kk * 128, kk ? 1 : i);
            wg_commit();
            if (i == nst - 1) bar_arrive(3 - wg, 256);
            wg_wait<1>();
            mbar_arrive_cl(rempty, GE + ((i + 3) & 3) * 8, i != 0);
            PROF(4, tid == 0 && (i & 3) == 0, 40 + (ps - 1) * 4 + i / 4);
          }
          wg_wait<0>();
          keep(ga); keep(gb);
#pragma unroll
          for (int i = 0; i < 64; i++) {
            asm volatile("mov.b32 %0, %1;" : "=f"(s[i]) : "f"(ga[i]));
            asm volatile("mov.b32 %0, %1;" : "=f"(o[i]) : "f"(gb[i]));
          }
        }
        mbar_arrive_cl(rempty, GE + (ps == 2 ? 24 : 8));
        if (ps == 2) break;
      }
      const uint32_t qw = base + wg * 8192, qt = QT >> (16 * ps), at = ps ? AT1 : AT0;
      {
        const uint32_t wt = ps ? WT1 : WT0;
        const uint64_t da0 = make_desc(qw + unit_of(qt, 2), 16, 1024), da1 = make_desc(qw + unit_of(qt, 3), 16, 1024);
        const uint64_t db0 = make_desc(base + unit_of(wt, 2), 8192, 1024), db1 = make_desc(base + unit_of(wt, 3), 8192, 1024);
        mbar_wait(gfull + 16, 1);
        bar_sync(2 + wg, 256);
        wg_fence();
#pragma unroll
        for (int kk = 0; kk < 4; kk++) mma_ss<1>(s, da0 + kk * 2, db0 + kk * 128, 1);
        wg_commit();
        mbar_wait(xfull + 24, 1);
        mbar_wait(gfull + 24, 1);
        wg_fence();
#pragma unroll
        for (int kk = 0; kk < 4; kk++) mma_ss<1>(s, da1 + kk * 2, db1 + kk * 128, 1);
        wg_commit();
        bar_arrive(3 - wg, 256);
        mbar_wait(ps == 0 ? bar_pread : bar_ofree + 8, 0);
        wg_wait<0>();
        keep(s);
        PROF(2, tid == 0, 8 + ps * 8);
        uint32_t q[32];
        pack_p(s, q);
#pragma unroll
        for (int i = 0; i < 4; i++) stmatrix4((qw + unit_of(qt, 0) + frag_offset(warp)) ^ (i << 5), q[4 * i], q[4 * i + 1], q[4 * i + 2], q[4 * i + 3]);
        keep(q);
        bar_sync(2 + wg, 256);
        wg_fence();
#pragma unroll
        for (int kk = 0; kk < 8; kk++) mma_ss<1>(o, (kk < 4 ? da0 : da1) + (kk & 3) * 2, (kk < 4 ? db0 : db1) + UNIT / 16 + (kk & 3) * 128, 1);
        wg_commit();
        mbar_wait(bfull, 0);
        wg_fence();
        const uint64_t dk = make_desc(base + unit_of(at, 0), 16, 1024);
#pragma unroll
        for (int kk = 0; kk < 8; kk++) mma_rs<0>(s, q[4 * kk], q[4 * kk + 1], q[4 * kk + 2], q[4 * kk + 3], dk + (kk >> 2) * 1024 + (kk & 3) * 2, kk != 0);
        wg_commit();
        bar_arrive(3 - wg, 256);
#pragma unroll
        for (int i = 4; i < 8; i++) stmatrix4((qw + unit_of(qt, 1) + frag_offset(warp)) ^ ((i & 3) << 5), q[4 * i], q[4 * i + 1], q[4 * i + 2], q[4 * i + 3]);
        wg_wait<1>();
        keep(o);
        mbar_arrive_cl(rempty, GE + 16);
        mbar_arrive_cl(rempty, GE + 24);
        store_chunk<0>(o, qw + unit_of(qt, 2) + frag_offset(warp));
        store_chunk<1>(o, qw + unit_of(qt, 3) + frag_offset(warp));
        wg_wait<0>();
        keep(s);
        mbar_arrive_cl(rempty, 0);
      }
      PROF(4, tid == 0 && ps == 1, 61);
      float l0 = 0.f, l1 = 0.f;
      auto step = [&](auto odd_c, const int j, uint32_t (&pw)[32], uint32_t (&pr)[32]) {
        constexpr bool ODD = decltype(odd_c)::value;
        const bool first = !ODD && (j & 2) == 0, last = ODD && j == 7;
        const uint32_t ph = (j >> 1) & 1;
        float i0, i1, a0, a1;
        const bool so = !ODD && j == 4;
        if (so) { i0 = inv_quad_sum(l0); i1 = inv_quad_sum(l1); l0 = 0.f; l1 = 0.f; }
        bool redo = !ODD && (j | ps) == 0;
        while (true) {
          if (redo) {
            float m0 = fmaxf(s[0], s[1]), m1 = fmaxf(s[2], s[3]);
#pragma unroll
            for (int i = 1; i < 16; i++) { m0 = fmaxf(m0, fmaxf(s[4 * i], s[4 * i + 1])); m1 = fmaxf(m1, fmaxf(s[4 * i + 2], s[4 * i + 3])); }
            m0 = fmaxf(m0, __shfl_xor_sync(0xffffffffu, m0, 1)); m1 = fmaxf(m1, __shfl_xor_sync(0xffffffffu, m1, 1));
            m0 = fmaxf(m0, __shfl_xor_sync(0xffffffffu, m0, 2)); m1 = fmaxf(m1, __shfl_xor_sync(0xffffffffu, m1, 2));
            m0 *= SCL2; m1 *= SCL2;
            if (!first) {
              m0 = fmaxf(m0, f0); m1 = fmaxf(m1, f1);
              const float c0 = ex2(f0 - m0), c1 = ex2(f1 - m1);
              l0 *= c0; l1 *= c1;
              wg_wait<0>();
              keep(o);
#pragma unroll
              for (int i = 0; i < 16; i++) { o[4 * i] *= c0; o[4 * i + 1] *= c0; o[4 * i + 2] *= c1; o[4 * i + 3] *= c1; }
            }
            f0 = m0; f1 = m1;
          }
          float b0 = 0.f, b1 = 0.f;
          a0 = 0.f; a1 = 0.f;
#pragma unroll
          for (int i = 0; i < 16; i++) {
            const float e0 = ex2(fmaf(s[4 * i], SCL2, -f0)), e1 = ex2(fmaf(s[4 * i + 1], SCL2, -f0));
            const float e2 = ex2(fmaf(s[4 * i + 2], SCL2, -f1)), e3 = ex2(fmaf(s[4 * i + 3], SCL2, -f1));
            a0 += e0; b0 += e1; a1 += e2; b1 += e3;
            pw[2 * i] = pack_bf(e0, e1); pw[2 * i + 1] = pack_bf(e2, e3);
            if (i == VREL) {
#pragma unroll
              for (int k = 0; k < 2 * VREL + 2; k++) asm volatile("" : "+r"(pw[k])::"memory");
              mbar_wait(bar_mod, 0);
              wg_wait<0>();
              mbar_arrive_cl(rempty, ODD ? 16 : 0, !redo && (ODD || j));
#pragma unroll
              for (int k = 4 * VREL + 4; k < 64; k++) asm volatile("" : "+f"(s[k])::"memory");
            }
          }
          a0 += b0; a1 += b1;
          if (redo) break;
          redo = __any_sync(0xffffffffu, !(a0 + a1 < 0x1p90f));
          if (first) {
            uint32_t m0 = __ballot_sync(0xffffffffu, a0 > 0x1p-80f), m1 = __ballot_sync(0xffffffffu, a1 > 0x1p-80f);
            m0 |= m0 >> 1; m1 |= m1 >> 1; m0 |= m0 >> 2; m1 |= m1 >> 2;
            redo = redo || (m0 & m1 & 0x11111111u) != 0x11111111u;
          }
          if (!redo) break;
        }
        l0 += a0; l1 += a1;
        keep(pw);
        keep(o);
        if (so) store_chunk<0>(o, i0, i1, qw + unit_of(qt, 0) + frag_offset(warp));
        keep(o);
        if (j == (ODD ? 5 : 0)) { fence_async_smem(); if (ODD) mbar_arrive(bar_ofull + wg * 8); }
        mbar_wait(bfull + (ODD ? 24 : 8), ph);
        bar_sync(2 + wg, 256);
        if (!last) {
          const uint32_t qn = qt >> (j >= 3 ? 8 : 0);
          wg_fence();
          issue_qk(s, qw + unit_of(qn, 0), qw + unit_of(qn, 1), base + unit_of(at, ODD ? 3 : 1));
          wg_commit();
          mbar_wait(bfull + (ODD ? 0 : 16), ODD ? ph ^ 1 : ph);
        }
        if (so) { store_chunk<1>(o, i0, i1, qw + unit_of(qt, 1) + frag_offset(warp)); keep(o); }
        wg_fence();
        issue_pv(o, pw, base + unit_of(at, ODD ? (last ? 3 : 0) : 2), !first);
        wg_commit();
        bar_arrive(3 - wg, 256);
        wg_wait<1>();
        keep(s);
        mbar_arrive_cl(rempty, ODD ? 24 : 8, !last);
        PROF(4, tid == 0 && ps == 1, 51 + j);
      };
      uint32_t pa[32], pb[32];
#pragma unroll 1
      for (int j = 0; j < 8; j += 2) {
        step(std::false_type{}, j, pa, pb);
        step(std::true_type{}, j + 1, pb, pa);
      }
      {
        const float i0 = inv_quad_sum(l0), i1 = inv_quad_sum(l1);
        wg_wait<0>();
        keep(o);
        mbar_arrive_cl(rempty, 24);
        store_chunk<0>(o, i0, i1, qw + unit_of(qt, 2) + frag_offset(warp));
        store_chunk<1>(o, i0, i1, qw + unit_of(qt, 3) + frag_offset(warp));
        fence_async_smem();
        mbar_arrive(bar_ofull + 16 + wg * 8);
      }
      PROF(2, tid == 0, 10 + ps * 8);
    }

    const int ln = fresh_lane(), g = ln >> 2, tq = ln & 3, ct = warp * 32 + ln;
    const bool lane0 = ln == 0;
    const int lrow0 = warp * 16 + g;
    const int grow0 = rb * 128 + lrow0;
    const uint32_t res = base + OFF_RES, trow = res + wg * 8192 + frag_offset(warp);
    uint32_t xr[32];
    uint4 sv[4], own;
    uint32_t* sp[4];
#pragma unroll
    for (int k = 0; k < 4; k++) sp[k] = g_stats + ((((tq >> 1) * 4 + k) ^ cj) * SEQ + grow0 + (tq & 1) * 8) * 4;
    {
      const uint64_t da = make_desc(base + wg * 8192, 16, 1024), db = make_desc(base, 8192, 1024);
      constexpr int U = UNIT / 16;
#define HALF_STAGE(acc, xu, wu) _Pragma("unroll") for (int kk = 0; kk < 4; kk++) mma_ss<1>(acc, da + (xu) * U + kk * 2, db + (wu) * U + kk * 128, 1)
      PROF(10, ct == PT, 19); STAMP(0);
      cluster_arrive();
      mbar_wait(gfull, 1);
      mbar_wait(gfull + 8, 1);
      bar_sync(2 + wg, 256);
      wg_fence();
      HALF_STAGE(o, 7, 1);
      HALF_STAGE(o, 8, 3);
      wg_commit();
      STAMP(16);
      mbar_wait(gfull + 16, 1);
      STAMP(17);
      wg_fence();
      HALF_STAGE(o, 6, 11);
      wg_commit();
      bar_arrive(3 - wg, 256);
      mbar_wait(bar_par, 0);
      uint32_t* xo = g_xch + ((size_t)b * 8 * 256 + ct) * 4;
      const uint32_t* xi = g_xch + ((size_t)(b ^ 2) * 8 * 256 + ct) * 4;
      const uint32_t par1 = (~lds1(par + PAR_CONST + 4) & 1) << 16;
      wg_wait<1>();
      mbar_arrive_pred(bar_rel, lane0);
      wg_wait<0>();
      keep(o);
      mbar_arrive_pred(bar_ring, lane0);
      PROF(8, ct == PT, 20); STAMP(1);
#define SEND(i) st_b128(xo + (i) * 1024, (pack_bf(o[8 * (i)], o[8 * (i) + 1]) & ~0x10000u) | par1, pack_bf(o[8 * (i) + 2], o[8 * (i) + 3]), \
                        pack_bf(o[8 * (i) + 4], o[8 * (i) + 5]), pack_bf(o[8 * (i) + 6], o[8 * (i) + 7]))
#pragma unroll
      for (int i = 0; i < NS1; i++) SEND(i);
      PROF(8, ct == PT, 21); STAMP(2);
      bar_sync(2 + wg, 256);
      wg_fence();
      HALF_STAGE(s, 7, 0);
      HALF_STAGE(s, 8, 2);
      HALF_STAGE(s, 6, 10);
      wg_commit();
      bar_arrive(3 - wg, 256);
      STAMP(18);
      mbar_wait(gfull + 24, 1);
#pragma unroll
      for (int i = NS1; i < 8; i++) SEND(i);
      uint4 v[8];
#pragma unroll
      for (int i = 0; i < LD1; i++) v[i] = ld_b128(xi + i * 1024);
      STAMP(19);
      mbar_wait(bar_xres, 0);
      wg_wait<0>();
      mbar_arrive_pred(bar_ring + 8, lane0);
      bar_sync(2 + wg, 256);
      STAMP(20);
#pragma unroll
      for (int i = LD1; i < LD2; i++) v[i] = ld_b128(xi + i * 1024);
      mbar_wait(bar_xres, 0);
      wg_fence();
      HALF_STAGE(s, 9, 4);
      wg_commit();
      mbar_wait(bar_rx, 0);
      wg_fence();
      HALF_STAGE(s, 1, 5);
      wg_commit();
      bar_arrive(3 - wg, 256);
      STAMP(21);
#pragma unroll
      for (int i = LD2; i < 8; i++) v[i] = ld_b128(xi + i * 1024);
      if (LD2 < 8) mbar_wait(bar_xres, 0);
      wg_wait<0>();
      keep(s);
      mbar_arrive_pred(bar_ring + 16, lane0);
      PROF(10, ct == PT, 23); STAMP(4);
#pragma unroll
      for (int i = 0; i < 16; i += 2) ldmatrix4((trow ^ ((i & 7) << 4)) + (i >> 3) * 16384, xr[2 * i], xr[2 * i + 1], xr[2 * i + 2], xr[2 * i + 3]);
      uint32_t ga[16];
      uint4 bw[8];
#pragma unroll
      for (int i = 0; i < 8; i++) {
        if (!(i & 1)) {
          const uint4 t = lds4(par + PAR_SINK + i * 32 + tq * 16);
          ga[2 * i] = t.x; ga[2 * i + 1] = t.y; ga[2 * i + 2] = t.z; ga[2 * i + 3] = t.w;
        }
        bw[i] = lds4(par + PAR_T1 + i * 64 + tq * 16);
        if (!(g & 1)) { bw[i].x = 0x3f803f80u; bw[i].y = 0x3f803f80u; }
      }
      uint32_t pk[32];
      pack_p(s, pk);
      keep(pk);
      {
        uint32_t n = 0, miss;
        do {
          miss = 0;
#pragma unroll
          for (int i = 0; i < 8; i++) miss |= v[i].x ^ par1;
          miss = __any_sync(0xffffffffu, miss & 0x10000u);
          if (miss) {
#pragma unroll
            for (int i = 0; i < 8; i++)
              asm volatile("{ .reg .pred p; .reg .b32 t; xor.b32 t, %0, %5; and.b32 t, t, 0x10000; setp.ne.u32 p, t, 0;\n"
                           "@p ld.relaxed.gpu.global.v4.u32 {%0, %1, %2, %3}, [%4]; }"
                           : "+r"(v[i].x), "+r"(v[i].y), "+r"(v[i].z), "+r"(v[i].w) : "l"(xi + i * 1024), "r"(par1) : "memory");
          }
          watchdog(n);
        } while (miss);
      }
      PROF(8, ct == PT, 22); STAMP(3);
      float ds[4] = {0.f, 0.f, 0.f, 0.f}, dl[4] = {0.f, 0.f, 0.f, 0.f}, q0[4] = {0.f, 0.f, 0.f, 0.f}, q1[4] = {0.f, 0.f, 0.f, 0.f};
#pragma unroll
      for (int i = 0; i < 8; i++) {
        const uint32_t u0 = hfma2(ga[2 * i], hadd2(pk[4 * i], v[i].x & ~0x10000u), xr[4 * i]);
        const uint32_t u1 = hfma2(ga[2 * i], hadd2(pk[4 * i + 1], v[i].y), xr[4 * i + 1]);
        const uint32_t u2 = hfma2(ga[2 * i + 1], hadd2(pk[4 * i + 2], v[i].z), xr[4 * i + 2]);
        const uint32_t u3 = hfma2(ga[2 * i + 1], hadd2(pk[4 * i + 3], v[i].w), xr[4 * i + 3]);
        xr[4 * i] = u0; xr[4 * i + 1] = u1; xr[4 * i + 2] = u2; xr[4 * i + 3] = u3;
        mma16816(ds, u0, u1, u2, u3, bw[i].x, bw[i].y);
        mma16816(dl, u0, u1, u2, u3, bw[i].z, bw[i].w);
        mma16816(q0, u0, u1, u2, u3, u0, u2);
        mma16816(q1, u0, u1, u2, u3, u1, u3);
      }
      const float sqa = __shfl_sync(0xffffffffu, (g & 1) ? q0[1] : q0[0], g * 4 + (g >> 1));
      const float sqb = __shfl_sync(0xffffffffu, (g & 1) ? q1[3] : q1[2], g * 4 + (g >> 1));
      own = (tq & 1) ? make_uint4(__float_as_uint(ds[2]), __float_as_uint(sqb), __float_as_uint(ds[3] + dl[3]), tag)
                                 : make_uint4(__float_as_uint(ds[0]), __float_as_uint(sqa), __float_as_uint(ds[1] + dl[1]), tag);
      if (tq < 2) st_b128(sp[0], own.x, own.y, own.z, own.w);
#pragma unroll
      for (int k = 0; k < 4; k++) sv[k] = make_uint4(0, 0, 0, 0);
    }
    PROF(8, ct == PT, 29); STAMP(5);
    uint32_t mm, ih, il;
    float rbest;
    uint32_t wf[128];
    const uint32_t frow = (ln & 7) + (ln >> 4) * 8;
    const uint32_t wfo = base + (warp & 1) * 8192 + frow * 64 + ((((ln >> 3) & 1) ^ ((frow >> 1) & 3)) << 4);
#define LOAD_WF(m) _Pragma("unroll") for (int f = 0; f < 16; f++) {                                                   \
      const int r = ((f >> 1) * 4 + (m) * 2 + (f & 1)) * 4;                                                           \
      ldmatrix4t(((wfo + unit_of((m) ? FT_U : FT_G, warp >> 1)) ^ ((f & 1) * 32)) + (f >> 1) * 1024, wf[r], wf[r + 1], wf[r + 2], wf[r + 3]); \
    }
    bool early, early2 = false;
    {
#pragma unroll
      for (int i = 0; i < 16; i += 2) stmatrix4((trow ^ ((i & 7) << 4)) + (i >> 3) * 16384, xr[2 * i], xr[2 * i + 1], xr[2 * i + 2], xr[2 * i + 3]);
      const uint4 cst = lds4(par + PAR_CONST);
      const float A1 = __uint_as_float(cst.x), A2 = __uint_as_float(cst.z);
      uint32_t n = 0;
      early = false;
#pragma unroll 1
      while (true) {
        uint32_t miss;
        asm volatile("{ .reg .pred p0, p1, p2, p3; .reg .b64 u, v; .reg .b128 w;\n"
                     "setp.ge.u32 p0, %22, 2; setp.ne.and.u32 p0, %4, %21, p0; setp.ne.u32 p1, %8, %21; setp.ne.u32 p2, %12, %21; setp.ne.u32 p3, %16, %21;\n"
                     "@p0 ld.relaxed.gpu.global.v4.u32 {%1, %2, %3, %4}, [%17];\n"
                     "@p1 ld.relaxed.gpu.global.v4.u32 {%5, %6, %7, %8}, [%18];\n"
                     "@p2 ld.relaxed.gpu.global.v4.u32 {%9, %10, %11, %12}, [%19];\n"
                     "@p3 ld.relaxed.gpu.global.v4.u32 {%13, %14, %15, %16}, [%20];\n"
                     "or.pred p0, p0, p1; or.pred p2, p2, p3; or.pred p0, p0, p2; vote.sync.any.pred p0, p0, 0xffffffff; selp.u32 %0, 1, 0, p0; }"
                     : "=r"(miss), "+r"(sv[0].x), "+r"(sv[0].y), "+r"(sv[0].z), "+r"(sv[0].w), "+r"(sv[1].x), "+r"(sv[1].y), "+r"(sv[1].z), "+r"(sv[1].w),
                       "+r"(sv[2].x), "+r"(sv[2].y), "+r"(sv[2].z), "+r"(sv[2].w), "+r"(sv[3].x), "+r"(sv[3].y), "+r"(sv[3].z), "+r"(sv[3].w)
                     : "l"(sp[0]), "l"(sp[1]), "l"(sp[2]), "l"(sp[3]), "r"(tag), "r"(tq) : "memory");
        if (!miss) break;
        if (!early && (b >= NFFN || __all_sync(0xffffffffu, mbar_test(bar_box + (warp >> 1) * 8, 0)))) {
          early = true;
          LOAD_WF(0);
          __syncwarp();
          mbar_arrive_pred(bar_gate, lane0);
        } else if (UPE && early && !early2 && (b >= NFFN || __all_sync(0xffffffffu, mbar_test(bar_box + (4 + (warp >> 1)) * 8, 0)))) {
          early2 = true;
          LOAD_WF(1);
        }
        watchdog(n);
      }
      const uint4 v0 = tq < 2 ? own : sv[0], v1 = sv[1], v2 = sv[2], v3 = sv[3];
      PROF(8, ct == PT, 30); STAMP(6);
      float su = (__uint_as_float(v0.x) + __uint_as_float(v1.x)) + (__uint_as_float(v2.x) + __uint_as_float(v3.x));
      float sq = (__uint_as_float(v0.y) + __uint_as_float(v1.y)) + (__uint_as_float(v2.y) + __uint_as_float(v3.y));
      float dt = (__uint_as_float(v0.z) + __uint_as_float(v1.z)) + (__uint_as_float(v2.z) + __uint_as_float(v3.z));
      su += __shfl_xor_sync(0xffffffffu, su, 2); sq += __shfl_xor_sync(0xffffffffu, sq, 2); dt += __shfl_xor_sync(0xffffffffu, dt, 2);
      const float m = su * (1.f / DM);
      float mb, sd;
      ln_scalars(m, fmaxf(sq * (1.f / DM) - m * m, 0.f), mb, sd);
      const float inv = rcp(sd);
      rbest = (dt - mb * A1) * inv + A2;
      mm = pack_bf(mb, mb);
      ih = pack_bf(inv, inv);
      const float lo = inv - bf_lo(ih);
      il = pack_bf(lo, lo);
    }
    int ibest;
    {
      const uint32_t bits = __float_as_uint(rbest);
      const uint32_t key = (((int)bits < 0 ? ~bits : bits | 0x80000000u) & ~0x1ffu) | ((127 - lrow0 - (tq & 1) * 8) << 2) | tag;
      sts1(par + PAR_RED + warp * 4, __reduce_max_sync(0xffffffffu, key));
      PROF(8, ct == PT, 38); STAMP(7);
      bar_sync(1, 256);
      const uint4 ka = lds4(par + PAR_RED), kb = lds4(par + PAR_RED + 16);
      const uint32_t k2 = max(max(max(ka.x, ka.y), max(ka.z, ka.w)), max(max(kb.x, kb.y), max(kb.z, kb.w)));
      if (ct == 0 && cj == 0) st_relaxed(g_cand + rb, k2);
      ibest = 127 - ((k2 >> 2) & 127);
    }
    PROF(8, ct == PT, 39); STAMP(8);
    if ((ibest >> 4) == warp) {
      const int src = (ibest & 7) * 4 + ((ibest >> 3) & 1), ch = g * 2;
      const uint32_t cm = __shfl_sync(0xffffffffu, mm, src), ch_ = __shfl_sync(0xffffffffu, ih, src), cl = __shfl_sync(0xffffffffu, il, src);
      const uint32_t xa = res + (ch >> 3) * 16384 + ibest * 128 + (((ch & 7) ^ (ibest & 7)) << 4) + tq * 4;
      const uint32_t x0 = lds1(xa), x1 = lds1(xa ^ 16);
      const uint2 p0 = lds2(par + PAR_T2 + ch * 64 + tq * 16), p1 = lds2(par + PAR_T2 + ch * 64 + 64 + tq * 16);
      uint32_t* dst = g_row + rb * 2 * DM + cj * 128 + ln * 4;
      st_pairs(dst, ln_mod(x0, cm, ch_, cl, p0.x, p0.y), ln_mod(x1, cm, ch_, cl, p1.x, p1.y), tag);
      st_pairs(dst + DM, x0, x1, tag);
      __syncwarp();
    }
    PROF(8, ct == PT, 37); STAMP(9);
    const bool cand = (ibest >> 4) == warp;
    auto out_half = [&](int hf) {
      const uint32_t mm0 = __shfl_sync(0xffffffffu, mm, ln & ~1), mm1 = __shfl_sync(0xffffffffu, mm, ln | 1);
      const uint32_t ih0 = __shfl_sync(0xffffffffu, ih, ln & ~1), ih1 = __shfl_sync(0xffffffffu, ih, ln | 1);
      const uint32_t il0 = __shfl_sync(0xffffffffu, il, ln & ~1), il1 = __shfl_sync(0xffffffffu, il, ln | 1);
      uint32_t x[16];
#pragma unroll
      for (int i = 0; i < 8; i += 2) ldmatrix4((trow ^ (i << 4)) + hf * 16384, x[2 * i], x[2 * i + 1], x[2 * i + 2], x[2 * i + 3]);
#pragma unroll
      for (int i = 0; i < 8; i++) {
        const uint4 pv = lds4(par + PAR_T2 + (hf * 8 + i) * 64 + tq * 16);
        x[2 * i] = OMUL(OMUL(ln_norm(x[2 * i], mm0, ih0, il0), pv.x, pv.y), pv.z, x[2 * i]);
        x[2 * i + 1] = OMUL(OMUL(ln_norm(x[2 * i + 1], mm1, ih1, il1), pv.x, pv.y), pv.z, x[2 * i + 1]);
      }
#pragma unroll
      for (int i = 0; i < 8; i += 2) stmatrix4((trow ^ (i << 4)) + hf * 16384, x[2 * i], x[2 * i + 1], x[2 * i + 2], x[2 * i + 3]);
      if (!cand) fence_async_smem();
      __syncwarp();
      if (!cand && elect_one()) {
        tma2d_store(&maps.out, res + hf * 16384 + warp * 2048, cj * 128 + hf * 64, rb * 128 + warp * 16);
        asm volatile("cp.async.bulk.commit_group;" ::: "memory");
      }
    };
    const int pre = b >= NFFN ? 2 : (LNP == 2 ? 1 : (early2 ? LNP : 0));
#pragma unroll 1
    for (int hf = 0; hf < pre; hf++) out_half(hf);
    uint32_t wd[64];
    const uint32_t wda = base + unit_of(FT_D, warp >> 1) + (warp & 1) * 8192 + frow * 128 + ((((ln >> 3) & 1) ^ (ln & 7)) << 4);
#define LOAD_WD(f) ldmatrix4t((wda ^ ((((f) >> 1) & 3) * 32)) + ((f) >> 3) * 4096 + ((f) & 1) * 2048, wd[4 * (f)], wd[4 * (f) + 1], wd[4 * (f) + 2], wd[4 * (f) + 3])
    if (!early) {
      if (b < NFFN) mbar_wait(bar_box + (warp >> 1) * 8, 0);
      LOAD_WF(0);
      __syncwarp();
      mbar_arrive_pred(bar_gate, lane0);
    }
    if (b < NFFN) {
      const uint32_t own = base + unit_of(FT_G, warp >> 1) + (warp & 1) * 8192;
      if (!early2) {
        mbar_wait(bar_box + (4 + (warp >> 1)) * 8, 0);
        LOAD_WF(1);
      }
      uint32_t* const ydst = g_ypart + ((size_t)(warp * 16 + tq * 2) * NFFN + b) * 8 + g;
      PROF(8, ct == PT, 31); STAMP(10);
      bool wdok;
      {
        uint32_t n = 0;
        while (!(wdok = __all_sync(0xffffffffu, mbar_test(bar_box + (8 + (warp >> 1)) * 8, 0))) && !__all_sync(0xffffffffu, mbar_test(bar_sel, 0))) watchdog(n);
      }
      if (wdok) {
#pragma unroll
        for (int f = 0; f < 16; f++) LOAD_WD(f);
      }
      STAMP(11);
      mbar_wait(bar_sel, 0);
      PROF(8, ct == PT, 33); STAMP(12);
      float d[8][4];
#pragma unroll
      for (int i = 0; i < 4; i++) { d[i][0] = 0.f; d[i][1] = 0.f; d[i][2] = 0.f; d[i][3] = 0.f; }
#pragma unroll
      for (int ks = 0; ks < 8; ks++) {
        const uint2 hb = lds2(own + 256 + ks * 32 + tq * 8);
#pragma unroll
        for (int mt = 0; mt < 4; mt++) {
          const int r = ks * 16 + mt * 4;
          mma16816(d[mt], wf[r], wf[r + 1], wf[r + 2], wf[r + 3], hb.x, hb.y);
        }
      }
      sts2(own + (tq * 8 + g) * 8, __float_as_uint((tq & 2) ? ((tq & 1) ? d[1][2] : d[1][0]) : ((tq & 1) ? d[0][2] : d[0][0])),
           __float_as_uint((tq & 2) ? ((tq & 1) ? d[3][2] : d[3][0]) : ((tq & 1) ? d[2][2] : d[2][0])));
      bar_sync(1, 256);
      uint32_t ab[4];
      {
        float G = 0.f, U = 0.f;
        uint2 pv[8];
#pragma unroll
        for (int w8 = 0; w8 < 8; w8++) pv[w8] = lds2(base + ln * 8 + ((FT_G >> (w8 >> 1) * 4) & 15) * UNIT + (w8 & 1) * 8192);
#pragma unroll
        for (int w8 = 0; w8 < 8; w8 += 2) {
          G += __uint_as_float(pv[w8].x) + __uint_as_float(pv[w8 + 1].x);
          U += __uint_as_float(pv[w8].y) + __uint_as_float(pv[w8 + 1].y);
        }
        const float act = rbf(silu_f(rbf(G))) * rbf(U);
        const uint32_t pk = pack_bf(act, __shfl_down_sync(0xffffffffu, act, 1));
#pragma unroll
        for (int i = 0; i < 4; i++) ab[i] = __shfl_sync(0xffffffffu, pk, i * 8 + tq * 2);
      }
      if (!wdok) {
        mbar_wait(bar_box + (8 + (warp >> 1)) * 8, 0);
#pragma unroll
        for (int f = 0; f < 16; f++) LOAD_WD(f);
      }
      PROF(8, ct == PT, 34); STAMP(13);
#pragma unroll
      for (int mt = 0; mt < 8; mt++) {
        d[mt][0] = 0.f; d[mt][1] = 0.f; d[mt][2] = 0.f; d[mt][3] = 0.f;
        mma16816(d[mt], wd[mt * 8], wd[mt * 8 + 1], wd[mt * 8 + 2], wd[mt * 8 + 3], ab[0], ab[1]);
        mma16816(d[mt], wd[mt * 8 + 4], wd[mt * 8 + 5], wd[mt * 8 + 6], wd[mt * 8 + 7], ab[2], ab[3]);
      }
#pragma unroll
      for (int i = 0; i < 4; i++) {
        const int m4 = (i >> 1) * 4, e = (i & 1) * 2;
        const float y = (tq & 2) ? ((tq & 1) ? d[m4 + 3][e] : d[m4 + 2][e]) : ((tq & 1) ? d[m4 + 1][e] : d[m4][e]);
        st_relaxed(ydst + (m4 * 2 + (i & 1)) * NFFN * 8, tagf(y, tag));
      }
      PROF(8, ct == PT, 35); STAMP(14);
    }
    mbar_wait(bar_sel, 0);
    mbar_arrive_pred(bar_win, ct == 0);
    const int iwin = lds1(par + PAR_CONST + 60) & 0x7ff;
#pragma unroll 1
    for (int hf = pre; hf < 2; hf++) out_half(hf);
    if (cand) {
      const int wrow0 = warp * 16;
#pragma unroll 2
      for (int p = 0; p < 8; p++) {
        const int row = 2 * p + (ln >> 4), ch = ln & 15;
        const uint4 v = lds4(res + (ch >> 3) * 16384 + (wrow0 + row) * 128 + (((ch & 7) ^ (row & 7)) << 4));
        if (rb * 128 + wrow0 + row != iwin) *reinterpret_cast<uint4*>(P.out + (size_t)(rb * 128 + wrow0 + row) * DM + cj * 128 + ch * 8) = v;
      }
    }
    asm volatile("cp.async.bulk.wait_group.read 0;" ::: "memory");
    PROF(8, ct == PT, 11); STAMP(15);
    cluster_wait();
  }
}

typedef CUresult (*EncodeFn)(CUtensorMap*, CUtensorMapDataType, cuuint32_t, void*, const cuuint64_t*, const cuuint64_t*,
                             const cuuint32_t*, const cuuint32_t*, CUtensorMapInterleave, CUtensorMapSwizzle,
                             CUtensorMapL2promotion, CUtensorMapFloatOOBfill);

void map2d(EncodeFn enc, CUtensorMap* m, const void* p, uint64_t rows, uint64_t cols, uint32_t brows) {
  cuuint64_t dims[2] = {cols, rows}, strides[1] = {cols * 2};
  cuuint32_t box[2] = {64, brows}, es[2] = {1, 1};
  enc(m, CU_TENSOR_MAP_DATA_TYPE_BFLOAT16, 2, const_cast<void*>(p), dims, strides, box, es, CU_TENSOR_MAP_INTERLEAVE_NONE,
      CU_TENSOR_MAP_SWIZZLE_128B, CU_TENSOR_MAP_L2_PROMOTION_L2_256B, CU_TENSOR_MAP_FLOAT_OOB_FILL_NONE);
}
void map2d_narrow(EncodeFn enc, CUtensorMap* m, const void* p, uint64_t rows, uint64_t cols, uint32_t brows) {
  cuuint64_t dims[2] = {cols, rows}, strides[1] = {cols * 2};
  cuuint32_t box[2] = {32, brows}, es[2] = {1, 1};
  enc(m, CU_TENSOR_MAP_DATA_TYPE_BFLOAT16, 2, const_cast<void*>(p), dims, strides, box, es, CU_TENSOR_MAP_INTERLEAVE_NONE,
      CU_TENSOR_MAP_SWIZZLE_64B, CU_TENSOR_MAP_L2_PROMOTION_L2_64B, CU_TENSOR_MAP_FLOAT_OOB_FILL_NONE);
}
void map3d(EncodeFn enc, CUtensorMap* m, const void* p, uint64_t rows, uint64_t cols, uint32_t brows, uint32_t nch) {
  cuuint64_t dims[3] = {64, rows, cols / 64}, strides[2] = {cols * 2, 128};
  cuuint32_t box[3] = {64, brows, nch}, es[3] = {1, 1, 1};
  enc(m, CU_TENSOR_MAP_DATA_TYPE_BFLOAT16, 3, const_cast<void*>(p), dims, strides, box, es, CU_TENSOR_MAP_INTERLEAVE_NONE,
      CU_TENSOR_MAP_SWIZZLE_128B, CU_TENSOR_MAP_L2_PROMOTION_L2_256B, CU_TENSOR_MAP_FLOAT_OOB_FILL_NONE);
}

}

extern "C" void kernel_launch(void* const* d_in, const int* in_sizes, int n_in, void* d_out, int out_size) {
  (void)in_sizes; (void)n_in; (void)out_size;
  static EncodeFn enc = nullptr;
  if (!enc) {
    void* fn = nullptr;
    cudaDriverEntryPointQueryResult st;
    cudaGetDriverEntryPoint("cuTensorMapEncodeTiled", &fn, cudaEnableDefault, &st);
    enc = (EncodeFn)fn;
    cudaFuncSetAttribute(fused_kernel, cudaFuncAttributeMaxDynamicSharedMemorySize, SMEM_BYTES);
  }
  Maps maps;
  map2d(enc, &maps.x, d_in[0], SEQ, DM, 128);
  map2d(enc, &maps.out, d_out, SEQ, DM, 16);
  map3d(enc, &maps.wq, d_in[3], DM, NQ, 64, 2);
  map3d(enc, &maps.k, d_in[1], 4 * SK, 128, 128, 1);
  map3d(enc, &maps.v, d_in[2], 4 * SK, 128, 128, 1);
  map3d(enc, &maps.wo, d_in[4], NQ, DM, 64, 2);
  map2d_narrow(enc, &maps.wg, d_in[7], DM, FF, 256);
  map2d_narrow(enc, &maps.wu, d_in[8], DM, FF, 256);
  map3d(enc, &maps.wd, d_in[9], FF, DM, 32, 4);
  map2d_narrow(enc, &maps.wm, d_in[11], DM, NMOD, 256);
  Ptrs p;
  p.x = (const __nv_bfloat16*)d_in[0];
  p.w_r = (const __nv_bfloat16*)d_in[6];
  p.w_gate = (const __nv_bfloat16*)d_in[7];
  p.w_up = (const __nv_bfloat16*)d_in[8];
  p.w_down = (const __nv_bfloat16*)d_in[9];
  p.c = (const __nv_bfloat16*)d_in[10];
  p.w_mod = (const __nv_bfloat16*)d_in[11];
  p.out = (__nv_bfloat16*)d_out;
  fused_kernel<<<NMAIN + NHELP, 384, SMEM_BYTES>>>(maps, p);
}
```

```cpp
#include <cuda_runtime.h>
#include <cuda_bf16.h>
#include <cuda.h>
#include <stdint.h>
#include <type_traits>

#define HD 2
#define HDX 2
#define NRS 8
#define FPACE 3
#define GOST 20
#define WB 2
#define WN 20
#define RES0 17
#define RES1 20
#define HU 32
#define NS1 5
#define PG0 15
#define PSL 0
#define FB0 0
#define FB2 8
#define OPS 8192
#define OFL 0
#define ODS 8
#define MODUL hfma2
#define ODS1 5
#define LD1 0
#define LD2 4
#define FB1 2
#define FPB 8
#define FPACE0 2
#define OSL 900
#define OSL2 400
#define VREL 5
#define E0 3

namespace {

constexpr int SEQ = 2048, DM = 1024, NQ = 4096, SK = 2048, WIN = 512, FF = 3584, NMOD = 6144;
constexpr int NMAIN = 128, NHELP = 4, NFFN = 112;
constexpr int NSLOT = 4, SLOT_BYTES = 32768, UNIT = 16384, GST_BYTES = 3 * UNIT;
constexpr uint32_t XT1 = 0xDCBA, XT2 = 0x9687;
constexpr uint32_t WT0 = 0xA741, WT1 = 0x7420, WT2 = 0x4A20;
constexpr uint32_t AT0 = WT1, AT1 = WT2;
constexpr uint32_t QT = 0xDC9696DC;
constexpr int OFF_STAGE = 12 * UNIT;
constexpr uint32_t FT_G = 0x07B3, FT_U = 0xA628, FT_D = 0x5149;
constexpr int OFF_RES = 12 * UNIT;
constexpr int OFF_PAR = 14 * UNIT;
constexpr int OFF_BAR = OFF_PAR + 2528;
constexpr int SMEM_BYTES = OFF_BAR + 544;
static_assert(SMEM_BYTES <= 232448, "smem");

constexpr int PAR_T1 = 0;
constexpr int PAR_T2 = 512;
constexpr int PAR_CONST = 1536;
constexpr int PAR_RED = 1600;
constexpr int PAR_SINK = 2176;

struct Maps {
  CUtensorMap x, wq, k, v, wo, wg, wu, wd, wm, out;
};
struct Ptrs {
  const __nv_bfloat16 *x, *w_r, *c, *w_mod, *w_gate, *w_up, *w_down;
  __nv_bfloat16* out;
};

__device__ __align__(1024) uint8_t g_act[16 * 80 * UNIT];
__device__ __align__(128) uint32_t g_mod[NMOD];
__device__ __align__(128) uint32_t g_modp[2 * 2 * DM];
__device__ __align__(128) uint32_t g_ln1[SEQ * 4];
__device__ __align__(128) uint32_t g_cnt_h[16 * 32];
__device__ __align__(128) uint32_t g_cnt_o[128 * 32];
__device__ __align__(128) uint32_t g_xch[NMAIN * 8 * 256 * 4];
__device__ __align__(128) uint32_t g_stats[8 * SEQ * 4];
__device__ __align__(128) uint32_t g_cand[32];
__device__ __align__(128) uint32_t g_row[16 * 2 * DM];
__device__ __align__(128) uint32_t g_ypart[NMAIN * NFFN * 8];
__device__ uint32_t g_epoch;

__device__ __forceinline__ uint32_t fresh_lane() { uint32_t l; asm volatile("mov.u32 %0, %%laneid;" : "=r"(l)); return l; }
__device__ __forceinline__ uint32_t frag_offset(int warp) {
  const uint32_t l = fresh_lane();
  return ((warp & 3) * 16 + (l & 15)) * 128 + (((l >> 4) ^ (l & 7)) << 4);
}
__device__ __forceinline__ bool elect_one() {
  uint32_t p;
  asm volatile("{ .reg .pred q; elect.sync _|q, 0xffffffff; selp.u32 %0, 1, 0, q; }" : "=r"(p));
  return p;
}
__device__ __forceinline__ uint32_t smem_u32(const void* p) { return (uint32_t)__cvta_generic_to_shared(p); }
__device__ __forceinline__ void mbar_init(uint32_t bar, uint32_t cnt) {
  asm volatile("mbarrier.init.shared::cta.b64 [%0], %1;" ::"r"(bar), "r"(cnt) : "memory");
}
__device__ __forceinline__ void mbar_expect_tx(uint32_t bar, uint32_t bytes) {
  asm volatile("mbarrier.arrive.expect_tx.shared::cta.b64 _, [%0], %1;" ::"r"(bar), "r"(bytes) : "memory");
}
__device__ __forceinline__ void mbar_arrive(uint32_t bar) {
  asm volatile("mbarrier.arrive.shared::cta.b64 _, [%0];" ::"r"(bar) : "memory");
}
__device__ __forceinline__ void mbar_arrive_pred(uint32_t bar, bool p) {
  asm volatile("{ .reg .pred p; setp.ne.b32 p, %1, 0; @p mbarrier.arrive.shared::cta.b64 _, [%0]; }" ::"r"(bar), "r"((int)p) : "memory");
}
__device__ __forceinline__ void mbar_arrive_cl(uint32_t bar, uint32_t off, bool p = true) {
  asm volatile("{ .reg .pred p, q; .reg .b32 a; setp.ne.b32 q, %2, 0; setp.ne.and.b32 p, %0, 0, q; add.u32 a, %0, %1; @p mbarrier.arrive.shared::cluster.b64 _, [a]; }"
               ::"r"(bar), "r"(off), "r"((int)p) : "memory");
}
__device__ __forceinline__ uint32_t mapa(uint32_t addr, uint32_t cta) {
  uint32_t r; asm("mapa.shared::cluster.u32 %0, %1, %2;" : "=r"(r) : "r"(addr), "r"(cta)); return r;
}
__device__ __forceinline__ void cluster_arrive() { asm volatile("barrier.cluster.arrive.relaxed.aligned;" ::: "memory"); }
__device__ __forceinline__ void cluster_wait() { asm volatile("barrier.cluster.wait.aligned;" ::: "memory"); }
__device__ __forceinline__ void watchdog(uint32_t& n) {
}
__device__ __forceinline__ void mbar_wait(uint32_t bar, uint32_t parity) {
  asm volatile("{\n.reg .pred p;\nWAIT_%=:\nmbarrier.try_wait.parity.shared::cta.b64 p, [%0], %1;\n@!p bra WAIT_%=;\n}" ::"r"(bar), "r"(parity) : "memory");
}
__device__ __forceinline__ bool mbar_test(uint32_t bar, uint32_t parity) {
  uint32_t ok;
  asm volatile("{\n.reg .pred p;\nmbarrier.test_wait.parity.shared::cta.b64 p, [%1], %2;\nselp.u32 %0, 1, 0, p;\n}" : "=r"(ok) : "r"(bar), "r"(parity) : "memory");
  return ok;
}
__device__ __forceinline__ uint64_t l2_stream() {
  uint64_t f; asm("createpolicy.fractional.L2::evict_first.b64 %0, 1.0;" : "=l"(f)); return f;
}
__device__ __forceinline__ void tma2d(uint32_t dst, const CUtensorMap* m, int c0, int c1, uint32_t bar) {
  asm volatile("cp.async.bulk.tensor.2d.shared::cluster.global.mbarrier::complete_tx::bytes.L2::cache_hint [%0], [%1, {%3, %4}], [%2], %5;"
               ::"r"(dst), "l"(m), "r"(bar), "r"(c0), "r"(c1), "l"(l2_stream()) : "memory");
}
__device__ __forceinline__ void bulk_load(uint32_t dst, const void* src, uint32_t bytes, uint32_t bar) {
  asm volatile("cp.async.bulk.shared::cluster.global.mbarrier::complete_tx::bytes [%0], [%1], %2, [%3];" ::"r"(dst), "l"(src), "r"(bytes), "r"(bar) : "memory");
}
__device__ __forceinline__ void bulk_load_stream(uint32_t dst, const void* src, uint32_t bytes, uint32_t bar) {
  asm volatile("cp.async.bulk.shared::cluster.global.mbarrier::complete_tx::bytes.L2::cache_hint [%0], [%1], %2, [%3], %4;"
               ::"r"(dst), "l"(src), "r"(bytes), "r"(bar), "l"(l2_stream()) : "memory");
}
__device__ __forceinline__ void tma2d_store(const CUtensorMap* m, uint32_t src, int c0, int c1) {
  asm volatile("cp.async.bulk.tensor.2d.global.shared::cta.bulk_group [%0, {%2, %3}], [%1];" ::"l"(m), "r"(src), "r"(c0), "r"(c1) : "memory");
}
__device__ __forceinline__ void bulk_store(void* dst, uint32_t src, uint32_t bytes) {
  asm volatile("cp.async.bulk.global.shared::cta.bulk_group [%0], [%1], %2;" ::"l"(dst), "r"(src), "r"(bytes) : "memory");
}
__device__ __forceinline__ int slice_of(int i) { return i + ((i & 7) == 1) - ((i & 7) == 2); }
__device__ __forceinline__ uint32_t unit_of(uint32_t table, uint32_t i) { return ((table >> (i * 4)) & 15) * UNIT; }
__device__ __forceinline__ void tma3d(uint32_t dst, const CUtensorMap* m, int c0, int c1, int c2, uint32_t bar) {
  asm volatile("cp.async.bulk.tensor.3d.shared::cluster.global.mbarrier::complete_tx::bytes.L2::cache_hint [%0], [%1, {%3, %4, %5}], [%2], %6;"
               ::"r"(dst), "l"(m), "r"(bar), "r"(c0), "r"(c1), "r"(c2), "l"(l2_stream()) : "memory");
}
template <bool STREAM>
__device__ __forceinline__ void tma3d_mc(uint32_t dst, const CUtensorMap* m, int c0, int c1, int c2, uint32_t bar) {
  if (STREAM)
    asm volatile("cp.async.bulk.tensor.3d.shared::cluster.global.mbarrier::complete_tx::bytes.multicast::cluster.L2::cache_hint [%0], [%1, {%3, %4, %5}], [%2], %6, %7;"
                 ::"r"(dst), "l"(m), "r"(bar), "r"(c0), "r"(c1), "r"(c2), "h"((uint16_t)3), "l"(l2_stream()) : "memory");
  else
    asm volatile("cp.async.bulk.tensor.3d.shared::cluster.global.mbarrier::complete_tx::bytes.multicast::cluster [%0], [%1, {%3, %4, %5}], [%2], %6;"
                 ::"r"(dst), "l"(m), "r"(bar), "r"(c0), "r"(c1), "r"(c2), "h"((uint16_t)3) : "memory");
}
__device__ __forceinline__ void prefetch_map(const CUtensorMap* m) {
  asm volatile("prefetch.tensormap [%0];" ::"l"(m) : "memory");
}
__device__ __forceinline__ void fence_async() { asm volatile("fence.proxy.async.global;" ::: "memory"); }
__device__ __forceinline__ void fence_async_smem() { asm volatile("fence.proxy.async.shared::cta;" ::: "memory"); }
__device__ __forceinline__ void bar_sync(int id, int n) { asm volatile("bar.sync %0, %1;" ::"r"(id), "r"(n) : "memory"); }
__device__ __forceinline__ void bar_arrive(int id, int n) { asm volatile("bar.arrive %0, %1;" ::"r"(id), "r"(n) : "memory"); }
__device__ __forceinline__ void wg_fence() { asm volatile("wgmma.fence.sync.aligned;" ::: "memory"); }
__device__ __forceinline__ void wg_commit() { asm volatile("wgmma.commit_group.sync.aligned;" ::: "memory"); }
template <int N> __device__ __forceinline__ void wg_wait() { asm volatile("wgmma.wait_group.sync.aligned %0;" ::"n"(N) : "memory"); }
__device__ __forceinline__ uint64_t make_desc(uint32_t addr, uint32_t lbo, uint32_t sbo) {
  return (uint64_t)((addr & 0x3FFFF) >> 4) | ((uint64_t)(lbo >> 4) << 16) | ((uint64_t)(sbo >> 4) << 32) | (1ull << 62);
}
__device__ __forceinline__ uint32_t ld_relaxed(const uint32_t* p) {
  uint32_t v; asm volatile("ld.relaxed.gpu.global.u32 %0, [%1];" : "=r"(v) : "l"(p) : "memory"); return v;
}
__device__ __forceinline__ uint32_t ld_acquire(const uint32_t* p) {
  uint32_t v; asm volatile("ld.acquire.gpu.global.u32 %0, [%1];" : "=r"(v) : "l"(p) : "memory"); return v;
}
__device__ __forceinline__ uint4 ld_relaxed4(const uint32_t* p) {
  uint4 v; asm volatile("ld.relaxed.gpu.global.v4.u32 {%0,%1,%2,%3}, [%4];" : "=r"(v.x), "=r"(v.y), "=r"(v.z), "=r"(v.w) : "l"(p) : "memory"); return v;
}
__device__ __forceinline__ uint2 ld_relaxed2(const uint32_t* p) {
  uint2 v; asm volatile("ld.relaxed.gpu.global.v2.u32 {%0,%1}, [%2];" : "=r"(v.x), "=r"(v.y) : "l"(p) : "memory"); return v;
}
__device__ __forceinline__ void st_relaxed(uint32_t* p, uint32_t v) {
  asm volatile("st.relaxed.gpu.global.u32 [%0], %1;" ::"l"(p), "r"(v) : "memory");
}
__device__ __forceinline__ void st_relaxed2(uint32_t* p, uint32_t a, uint32_t b) {
  asm volatile("st.relaxed.gpu.global.v2.u32 [%0], {%1,%2};" ::"l"(p), "r"(a), "r"(b) : "memory");
}
__device__ __forceinline__ void st_relaxed4(uint32_t* p, uint32_t a, uint32_t b, uint32_t c, uint32_t d) {
  asm volatile("st.relaxed.gpu.global.v4.u32 [%0], {%1,%2,%3,%4};" ::"l"(p), "r"(a), "r"(b), "r"(c), "r"(d) : "memory");
}
__device__ __forceinline__ void st_b128(uint32_t* p, uint32_t a, uint32_t b, uint32_t c, uint32_t d) {
  asm volatile("{ .reg .b64 u, v; .reg .b128 w; mov.b64 u, {%1, %2}; mov.b64 v, {%3, %4}; mov.b128 w, {u, v}; st.relaxed.gpu.global.b128 [%0], w; }"
               ::"l"(p), "r"(a), "r"(b), "r"(c), "r"(d) : "memory");
}
__device__ __forceinline__ uint4 ld_b128(const uint32_t* p) {
  uint4 r;
  asm volatile("{ .reg .b64 u, v; .reg .b128 w; ld.relaxed.gpu.global.b128 w, [%4]; mov.b128 {u, v}, w; mov.b64 {%0, %1}, u; mov.b64 {%2, %3}, v; }"
               : "=r"(r.x), "=r"(r.y), "=r"(r.z), "=r"(r.w) : "l"(p) : "memory");
  return r;
}
__device__ __forceinline__ void st_pairs(uint32_t* p, uint32_t a, uint32_t b, uint32_t tag) {
  asm volatile("{ .reg .b64 u, v; mov.b64 u, {%1, %3}; mov.b64 v, {%2, %3}; st.relaxed.gpu.global.v2.b64 [%0], {u, v}; }"
               ::"l"(p), "r"(a), "r"(b), "r"(tag) : "memory");
}
__device__ __forceinline__ uint4 ld_pairs(const uint32_t* p) {
  uint4 v;
  asm volatile("{ .reg .b64 u, v; ld.relaxed.gpu.global.v2.b64 {u, v}, [%4]; mov.b64 {%0, %1}, u; mov.b64 {%2, %3}, v; }"
               : "=r"(v.x), "=r"(v.y), "=r"(v.z), "=r"(v.w) : "l"(p) : "memory");
  return v;
}
__device__ __forceinline__ uint2 ld_pair(const uint32_t* p) {
  uint2 v;
  asm volatile("{ .reg .b64 u; ld.relaxed.gpu.global.b64 u, [%2]; mov.b64 {%0, %1}, u; }" : "=r"(v.x), "=r"(v.y) : "l"(p) : "memory");
  return v;
}
__device__ __forceinline__ void red_release(uint32_t* p, uint32_t v) {
  asm volatile("red.release.gpu.global.add.u32 [%0], %1;" ::"l"(p), "r"(v) : "memory");
}
__device__ __forceinline__ uint32_t ldg_nc1(const void* p) {
  uint32_t v;
  asm volatile("ld.global.nc.u32 %0, [%1];" : "=r"(v) : "l"(p));
  return v;
}
__device__ __forceinline__ uint4 ldg_nc4(const void* p) {
  uint4 v; asm volatile("ld.global.nc.L1::no_allocate.v4.u32 {%0,%1,%2,%3}, [%4];" : "=r"(v.x), "=r"(v.y), "=r"(v.z), "=r"(v.w) : "l"(p)); return v;
}
__device__ __forceinline__ uint4 ldg_stream4(const void* p) {
  uint4 v;
  asm volatile("ld.global.nc.L1::no_allocate.L2::cache_hint.v4.u32 {%0,%1,%2,%3}, [%4], %5;" : "=r"(v.x), "=r"(v.y), "=r"(v.z), "=r"(v.w) : "l"(p), "l"(l2_stream()));
  return v;
}
__device__ __forceinline__ void stg4(void* p, uint4 v) {
  asm volatile("st.global.v4.u32 [%0], {%1,%2,%3,%4};" ::"l"(p), "r"(v.x), "r"(v.y), "r"(v.z), "r"(v.w) : "memory");
}
__device__ __forceinline__ void wait_counter(const uint32_t* p, uint32_t target) {
  uint32_t n = 0;
  while (__any_sync(0xffffffffu, (int)(ld_acquire(p) - target) < 0)) { watchdog(n); }
}
__device__ __forceinline__ uint32_t tagf(float v, uint32_t tag) { return (__float_as_uint(v) & ~3u) | tag; }
__device__ __forceinline__ bool tag_ok(uint4 v, uint32_t tag) { return (((v.x ^ tag) | (v.y ^ tag) | (v.z ^ tag) | (v.w ^ tag)) & 3u) == 0; }
__device__ __forceinline__ float untag_sum(uint32_t a, uint32_t b) { return __uint_as_float(a & ~3u) + __uint_as_float(b & ~3u); }
__device__ __forceinline__ uint4 poll4(const uint32_t* p, uint32_t tag) {
  uint4 v = ld_relaxed4(p);
  uint32_t n = 0;
  while (!__all_sync(0xffffffffu, tag_ok(v, tag))) { v = ld_relaxed4(p); watchdog(n); }
  return v;
}
__device__ __forceinline__ float bf_lo(uint32_t v) { return __uint_as_float(v << 16); }
__device__ __forceinline__ float bf_hi(uint32_t v) { return __uint_as_float(v & 0xffff0000u); }
__device__ __forceinline__ uint32_t pack_bf(float lo, float hi) {
  uint32_t r; asm("cvt.rn.bf16x2.f32 %0, %1, %2;" : "=r"(r) : "f"(hi), "f"(lo)); return r;
}
__device__ __forceinline__ float rbf(float v) { return __uint_as_float(pack_bf(0.f, v) & 0xffff0000u); }
__device__ __forceinline__ uint32_t hmul2(uint32_t a, uint32_t b) {
  uint32_t r; asm("mul.rn.bf16x2 %0, %1, %2;" : "=r"(r) : "r"(a), "r"(b)); return r;
}
__device__ __forceinline__ uint32_t hadd2(uint32_t a, uint32_t b) {
  uint32_t r; asm("add.rn.bf16x2 %0, %1, %2;" : "=r"(r) : "r"(a), "r"(b)); return r;
}
__device__ __forceinline__ uint32_t hsub2(uint32_t a, uint32_t b) {
  uint32_t r; asm("sub.rn.bf16x2 %0, %1, %2;" : "=r"(r) : "r"(a), "r"(b)); return r;
}
__device__ __forceinline__ uint32_t hmax2(uint32_t a, uint32_t b) {
  uint32_t r; asm("max.bf16x2 %0, %1, %2;" : "=r"(r) : "r"(a), "r"(b)); return r;
}
__device__ __forceinline__ float rcp(float x) { float r; asm("rcp.approx.ftz.f32 %0, %1;" : "=f"(r) : "f"(x)); return r; }
__device__ __forceinline__ float ex2(float x) { float r; asm("ex2.approx.ftz.f32 %0, %1;" : "=f"(r) : "f"(x)); return r; }
__device__ __forceinline__ void stmatrix4(uint32_t addr, uint32_t a, uint32_t b, uint32_t c, uint32_t d) {
  asm volatile("stmatrix.sync.aligned.m8n8.x4.shared.b16 [%0], {%1,%2,%3,%4};" ::"r"(addr), "r"(a), "r"(b), "r"(c), "r"(d) : "memory");
}
__device__ __forceinline__ void ldmatrix4(uint32_t addr, uint32_t& a, uint32_t& b, uint32_t& c, uint32_t& d) {
  asm volatile("ldmatrix.sync.aligned.m8n8.x4.shared.b16 {%0,%1,%2,%3}, [%4];" : "=r"(a), "=r"(b), "=r"(c), "=r"(d) : "r"(addr) : "memory");
}
__device__ __forceinline__ void ldmatrix4t(uint32_t addr, uint32_t& a, uint32_t& b, uint32_t& c, uint32_t& d) {
  asm volatile("ldmatrix.sync.aligned.m8n8.x4.trans.shared.b16 {%0,%1,%2,%3}, [%4];" : "=r"(a), "=r"(b), "=r"(c), "=r"(d) : "r"(addr) : "memory");
}
__device__ __forceinline__ void mma16816(float (&d)[4], uint32_t a0, uint32_t a1, uint32_t a2, uint32_t a3, uint32_t b0, uint32_t b1) {
  asm volatile("mma.sync.aligned.m16n8k16.row.col.f32.bf16.bf16.f32 {%0,%1,%2,%3}, {%4,%5,%6,%7}, {%8,%9}, {%0,%1,%2,%3};"
               : "+f"(d[0]), "+f"(d[1]), "+f"(d[2]), "+f"(d[3]) : "r"(a0), "r"(a1), "r"(a2), "r"(a3), "r"(b0), "r"(b1));
}
__device__ __forceinline__ void sts1(uint32_t a, uint32_t v) { asm volatile("st.shared.u32 [%0], %1;" ::"r"(a), "r"(v) : "memory"); }
__device__ __forceinline__ uint4 lds4(uint32_t a) {
  uint4 v; asm volatile("ld.shared.v4.u32 {%0,%1,%2,%3}, [%4];" : "=r"(v.x), "=r"(v.y), "=r"(v.z), "=r"(v.w) : "r"(a) : "memory"); return v;
}
__device__ __forceinline__ uint2 lds2(uint32_t a) {
  uint2 v; asm volatile("ld.shared.v2.u32 {%0,%1}, [%2];" : "=r"(v.x), "=r"(v.y) : "r"(a) : "memory"); return v;
}
__device__ __forceinline__ uint32_t lds1(uint32_t a) {
  uint32_t v; asm volatile("ld.shared.u32 %0, [%1];" : "=r"(v) : "r"(a) : "memory"); return v;
}
__device__ __forceinline__ void sts2(uint32_t a, uint32_t x, uint32_t y) { asm volatile("st.shared.v2.u32 [%0], {%1,%2};" ::"r"(a), "r"(x), "r"(y) : "memory"); }
__device__ __forceinline__ void sts4(uint32_t a, uint4 v) {
  asm volatile("st.shared.v4.u32 [%0], {%1,%2,%3,%4};" ::"r"(a), "r"(v.x), "r"(v.y), "r"(v.z), "r"(v.w) : "memory");
}
__device__ __forceinline__ float silu_f(float v) { return __fdividef(v, 1.f + __expf(-v)); }
__device__ __forceinline__ uint32_t hfma2(uint32_t a, uint32_t b, uint32_t c) {
  uint32_t r; asm("fma.rn.bf16x2 %0, %1, %2, %3;" : "=r"(r) : "r"(a), "r"(b), "r"(c)); return r;
}
__device__ __forceinline__ void split_inv(float sd, uint32_t& ih, uint32_t& il) {
  const float inv = rcp(sd);
  ih = pack_bf(inv, inv);
  const float lo = inv - bf_lo(ih);
  il = pack_bf(lo, lo);
}
__device__ __forceinline__ uint32_t ln_norm(uint32_t x, uint32_t mean2, uint32_t ih, uint32_t il) {
  const uint32_t d = hsub2(x, mean2);
  return hfma2(d, ih, hmul2(d, il));
}
__device__ __forceinline__ uint32_t modul(uint32_t n, uint32_t c1, uint32_t sh) { return hadd2(hmul2(n, c1), sh); }
__device__ __forceinline__ uint32_t ln_mod(uint32_t x, uint32_t mean2, uint32_t ih, uint32_t il, uint32_t c1, uint32_t sh) {
  return modul(ln_norm(x, mean2, ih, il), c1, sh);
}

#define R8(a, i) "+f"(a[i]), "+f"(a[i + 1]), "+f"(a[i + 2]), "+f"(a[i + 3]), "+f"(a[i + 4]), "+f"(a[i + 5]), "+f"(a[i + 6]), "+f"(a[i + 7])
#define D64 "{%0,%1,%2,%3,%4,%5,%6,%7,%8,%9,%10,%11,%12,%13,%14,%15,%16,%17,%18,%19,%20,%21,%22,%23,%24,%25,%26,%27,%28,%29,%30,%31," \
            "%32,%33,%34,%35,%36,%37,%38,%39,%40,%41,%42,%43,%44,%45,%46,%47,%48,%49,%50,%51,%52,%53,%54,%55,%56,%57,%58,%59,%60,%61,%62,%63}"
template <int TB>
__device__ __forceinline__ void mma_ss(float (&d)[64], uint64_t da, uint64_t db, int sc) {
  asm volatile("{\n.reg .pred p;\nsetp.ne.b32 p, %66, 0;\n"
               "wgmma.mma_async.sync.aligned.m64n128k16.f32.bf16.bf16 " D64 ", %64, %65, p, 1, 1, 0, %67;\n}"
               : R8(d, 0), R8(d, 8), R8(d, 16), R8(d, 24), R8(d, 32), R8(d, 40), R8(d, 48), R8(d, 56)
               : "l"(da), "l"(db), "r"(sc), "n"(TB));
}
template <int TB>
__device__ __forceinline__ void mma_rs(float (&d)[64], uint32_t a0, uint32_t a1, uint32_t a2, uint32_t a3, uint64_t db, int sc) {
  asm volatile("{\n.reg .pred p;\nsetp.ne.b32 p, %69, 0;\n"
               "wgmma.mma_async.sync.aligned.m64n128k16.f32.bf16.bf16 " D64 ", {%64,%65,%66,%67}, %68, p, 1, 1, %70;\n}"
               : R8(d, 0), R8(d, 8), R8(d, 16), R8(d, 24), R8(d, 32), R8(d, 40), R8(d, 48), R8(d, 56)
               : "r"(a0), "r"(a1), "r"(a2), "r"(a3), "l"(db), "r"(sc), "n"(TB));
}
#define D128 "{%0,%1,%2,%3,%4,%5,%6,%7,%8,%9,%10,%11,%12,%13,%14,%15,%16,%17,%18,%19,%20,%21,%22,%23,%24,%25,%26,%27,%28,%29,%30,%31," \
             "%32,%33,%34,%35,%36,%37,%38,%39,%40,%41,%42,%43,%44,%45,%46,%47,%48,%49,%50,%51,%52,%53,%54,%55,%56,%57,%58,%59,%60,%61,%62,%63," \
             "%64,%65,%66,%67,%68,%69,%70,%71,%72,%73,%74,%75,%76,%77,%78,%79,%80,%81,%82,%83,%84,%85,%86,%87,%88,%89,%90,%91,%92,%93,%94,%95," \
             "%96,%97,%98,%99,%100,%101,%102,%103,%104,%105,%106,%107,%108,%109,%110,%111,%112,%113,%114,%115,%116,%117,%118,%119,%120,%121,%122,%123,%124,%125,%126,%127}"
#define R128(d, e) R8(d, 0), R8(d, 8), R8(d, 16), R8(d, 24), R8(d, 32), R8(d, 40), R8(d, 48), R8(d, 56), \
                   R8(e, 0), R8(e, 8), R8(e, 16), R8(e, 24), R8(e, 32), R8(e, 40), R8(e, 48), R8(e, 56)
__device__ __forceinline__ void mma256_ss(float (&d)[64], float (&e)[64], uint64_t da, uint64_t db, int sc) {
  asm volatile("{\n.reg .pred p;\nsetp.ne.b32 p, %130, 0;\n"
               "wgmma.mma_async.sync.aligned.m64n256k16.f32.bf16.bf16 " D128 ", %128, %129, p, 1, 1, 0, 1;\n}"
               : R128(d, e) : "l"(da), "l"(db), "r"(sc));
}
__device__ __forceinline__ void mma256_rs(float (&d)[64], float (&e)[64], uint32_t a0, uint32_t a1, uint32_t a2, uint32_t a3, uint64_t db) {
  asm volatile("{\n.reg .pred p;\nsetp.ne.b32 p, 1, 0;\n"
               "wgmma.mma_async.sync.aligned.m64n256k16.f32.bf16.bf16 " D128 ", {%128,%129,%130,%131}, %132, p, 1, 1, 1;\n}"
               : R128(d, e) : "r"(a0), "r"(a1), "r"(a2), "r"(a3), "l"(db));
}
template <int N> __device__ __forceinline__ void keep(float (&a)[N]) {
#pragma unroll
  for (int i = 0; i < N; i++) asm volatile("" : "+f"(a[i])::"memory");
}
template <int N> __device__ __forceinline__ void keep(uint32_t (&a)[N]) {
#pragma unroll
  for (int i = 0; i < N; i++) asm volatile("" : "+r"(a[i])::"memory");
}

#define STAMP(idx) do {} while (0)
#define PROF(grp, cond, idx) do {} while (0)

constexpr float SCL2 = 1.4426950408889634f * 0.08838834764831845f;

__device__ __forceinline__ void pack_p(const float (&s)[64], uint32_t (&p)[32]) {
#pragma unroll
  for (int i = 0; i < 32; i++) p[i] = pack_bf(s[2 * i], s[2 * i + 1]);
}

__device__ __forceinline__ void issue_qk(float (&s)[64], uint32_t q0, uint32_t q1, uint32_t kslot) {
  const uint64_t db = make_desc(kslot, 16, 1024), da0 = make_desc(q0, 16, 1024), da1 = make_desc(q1, 16, 1024);
#pragma unroll
  for (int kk = 0; kk < 8; kk++) mma_ss<0>(s, (kk < 4 ? da0 : da1) + (kk & 3) * 2, db + (kk >> 2) * 1024 + (kk & 3) * 2, kk != 0);
}
__device__ __forceinline__ void issue_pv(float (&o)[64], uint32_t (&p)[32], uint32_t vslot, int acc) {
  uint64_t db = make_desc(vslot, 16384, 1024);
#pragma unroll
  for (int kk = 0; kk < 8; kk++)
    mma_rs<1>(o, p[4 * kk], p[4 * kk + 1], p[4 * kk + 2], p[4 * kk + 3], db + kk * 128, kk == 0 ? acc : 1);
}

template <int H>
__device__ __forceinline__ void store_chunk(const float (&a)[64], uint32_t addr) {
#pragma unroll
  for (int i = 8 * H; i < 8 * H + 8; i += 2)
    stmatrix4(addr ^ ((i & 7) << 4), pack_bf(a[4 * i], a[4 * i + 1]), pack_bf(a[4 * i + 2], a[4 * i + 3]),
              pack_bf(a[4 * i + 4], a[4 * i + 5]), pack_bf(a[4 * i + 6], a[4 * i + 7]));
}
template <int H>
__device__ __forceinline__ void store_chunk(const float (&a)[64], float i0, float i1, uint32_t addr) {
#pragma unroll
  for (int i = 8 * H; i < 8 * H + 8; i += 2)
    stmatrix4(addr ^ ((i & 7) << 4), pack_bf(a[4 * i] * i0, a[4 * i + 1] * i0), pack_bf(a[4 * i + 2] * i1, a[4 * i + 3] * i1),
              pack_bf(a[4 * i + 4] * i0, a[4 * i + 5] * i0), pack_bf(a[4 * i + 6] * i1, a[4 * i + 7] * i1));
}
__device__ __forceinline__ float inv_quad_sum(float l) {
  l += __shfl_xor_sync(0xffffffffu, l, 1);
  l += __shfl_xor_sync(0xffffffffu, l, 2);
  return rcp(l);
}

__device__ __forceinline__ void write_table(uint32_t table, bool ca, uint32_t t, const uint4& m0, const uint4& m1) {
  float c0 = untag_sum(m0.x, m1.x), c1 = untag_sum(m0.y, m1.y), c2 = untag_sum(m0.z, m1.z), c3 = untag_sum(m0.w, m1.w);
  if (ca) { c0 = 1.f + rbf(c0); c1 = 1.f + rbf(c1); c2 = 1.f + rbf(c2); c3 = 1.f + rbf(c3); }
  const uint32_t d = table + (t >> 2) * 64 + (t & 1) * 32 + (t & 2) * 2 + (ca ? 0 : 8);
  sts1(d, pack_bf(c0, c1));
  sts1(d + 16, pack_bf(c2, c3));
}

__device__ __forceinline__ void ln_scalars(float mean, float var, float& mb, float& sd) {
  mb = rbf(mean);
  float r; asm("sqrt.approx.ftz.f32 %0, %1;" : "=f"(r) : "f"(rbf(rbf(var) + 1e-5f)));
  sd = rbf(r);
}

__global__ void __cluster_dims__(2, 1, 1) __launch_bounds__(384, 1) fused_kernel(const __grid_constant__ Maps maps, const Ptrs P) {
  extern __shared__ __align__(1024) uint8_t smem_raw[];
  const uint32_t base = smem_u32(smem_raw);
  const int tid = threadIdx.x, lane = tid & 31;
  const int warp = __shfl_sync(0xffffffffu, tid >> 5, 0);
  const int b = blockIdx.x;
  PROF(31, tid == 0, 0);

  if (b >= NMAIN) {
    float* sc = reinterpret_cast<float*>(smem_raw);
    float* red = sc + DM;
    for (int k = tid; k < DM; k += 384) sc[k] = rbf(silu_f(__bfloat162float(P.c[k])));
    __syncthreads();
    if (tid < 256) {
      const int col = 2048 + (b - NMAIN) * 1024 + (tid & 127) * 8, r0 = (tid >> 7) * 512;
      float acc[8];
#pragma unroll
      for (int e = 0; e < 8; e++) acc[e] = 0.f;
#pragma unroll 1
      for (int r = r0; r < r0 + 512; r += HU) {
        uint4 w[HU];
#pragma unroll
        for (int u = 0; u < HU; u++) w[u] = ldg_stream4(P.w_mod + (size_t)(r + u) * NMOD + col);
#pragma unroll
        for (int u = 0; u < HU; u++) {
          float s = sc[r + u];
          acc[0] += s * bf_lo(w[u].x); acc[1] += s * bf_hi(w[u].x); acc[2] += s * bf_lo(w[u].y); acc[3] += s * bf_hi(w[u].y);
          acc[4] += s * bf_lo(w[u].z); acc[5] += s * bf_hi(w[u].z); acc[6] += s * bf_lo(w[u].w); acc[7] += s * bf_hi(w[u].w);
        }
      }
      if (tid >= 128) {
#pragma unroll
        for (int e = 0; e < 8; e++) red[(tid & 127) * 8 + e] = acc[e];
      }
      const uint32_t tag = ld_relaxed(&g_epoch) % 3 + 1;
      bar_sync(1, 256);
      if (tid < 128) {
        uint32_t o[8];
#pragma unroll
        for (int e = 0; e < 8; e++) o[e] = __float_as_uint(rbf(acc[e] + red[tid * 8 + e])) | tag;
        st_relaxed4(g_mod + col, o[0], o[1], o[2], o[3]);
        st_relaxed4(g_mod + col + 4, o[4], o[5], o[6], o[7]);
        const uint4 wr = ldg_nc4(P.w_r + tid * 8);
        const uint32_t wv[4] = {wr.x, wr.y, wr.z, wr.w};
        float dsum = 0.f;
#pragma unroll
        for (int e = 0; e < 8; e++) {
          const float m = bf_hi(o[e]);
          dsum += (b == NMAIN + 2 ? rbf(1.f + m) : m) * ((e & 1) ? bf_hi(wv[e >> 1]) : bf_lo(wv[e >> 1]));
        }
#pragma unroll
        for (int k = 16; k > 0; k >>= 1) dsum += __shfl_xor_sync(0xffffffffu, dsum, k);
        if (lane == 0) st_relaxed(g_mod + (b - NMAIN) * 4 + warp, tagf(dsum, tag));
      }
    }
    PROF(2, tid == 0, 1);
    return;
  }

  const int rank = b & 1;
  const int rb = ((b >> 4) << 1) | rank, cj = (b >> 1) & 7;
  const bool late = b & 4;
  const uint32_t bfull = base + OFF_BAR, bempty = bfull + NSLOT * 8;
  const uint32_t gfull = bempty + NSLOT * 8, gempty = gfull + 32;
  const uint32_t bar_ofull = gempty + 32;
  const uint32_t bar_ofree = bar_ofull + 32;
  const uint32_t bar_par = bar_ofree + 32;
  const uint32_t bar_mod = bar_par + 8;
  const uint32_t bar_pread = bar_mod + 8;
  const uint32_t bar_xres = bar_pread + 8;
  const uint32_t bar_ring = bar_xres + 8;
  const uint32_t bar_box = bar_ring + 24;
  const uint32_t bar_go = bar_box + 96;
  const uint32_t bar_go2 = bar_go + 16;
  const uint32_t bar_cnt = bar_go + 24;
  const uint32_t xfull = bar_go + 40, xempty = xfull + 32;
  const uint32_t bar_hw = xempty + 32, bar_hx = bar_hw + 8;
  const uint32_t bar_hpub = bar_hx + 16;
  const uint32_t bar_win = bar_hpub + 16;
  const uint32_t bar_rx = bar_win + 8;
  const uint32_t bar_sel = bar_rx + 8;
  const uint32_t bar_gate = bar_sel + 8;
  const uint32_t bar_rel = bar_gate + 8;
  const uint32_t bar_od = bar_rel + 8;
  const uint32_t bar_mod2 = bar_od + 8;
  const uint32_t bar_res = bar_go + 8;
  const uint32_t stage = base + OFF_STAGE, par = base + OFF_PAR;

  if (warp == 10 && elect_one()) prefetch_map(&maps.wm);
  if (warp == 8 && elect_one()) {
    for (int s = 0; s < NSLOT; s++) { mbar_init(bfull + s * 8, 1); mbar_init(bempty + s * 8, 16); }
    for (int s = 0; s < 4; s++) { mbar_init(gfull + s * 8, 1); mbar_init(gempty + s * 8, 16); mbar_init(xfull + s * 8, 1); mbar_init(xempty + s * 8, 8); mbar_init(bar_ofree + s * 8, 1); mbar_init(bar_ofull + s * 8, 128); }
    mbar_init(bar_par, 64); mbar_init(bar_mod, 256); mbar_init(bar_pread, 2); mbar_init(bar_xres, 1);
    mbar_init(bar_ring, 8); mbar_init(bar_ring + 8, 8); mbar_init(bar_ring + 16, 8);
    mbar_init(bar_go, 1); mbar_init(bar_go2, 1); mbar_init(bar_cnt, 1); mbar_init(bar_cnt + 8, 1); mbar_init(bar_hpub, 8); mbar_init(bar_hpub + 8, 8); mbar_init(bar_res, 1); mbar_init(bar_win, 1); mbar_init(bar_rx, 1); mbar_init(bar_sel, 64); mbar_init(bar_gate, 8); mbar_init(bar_rel, 8); mbar_init(bar_od, 1); mbar_init(bar_mod2, 64);
    for (int s = 0; s < 12; s++) mbar_init(bar_box + s * 8, 1);
    asm volatile("fence.mbarrier_init.release.cluster;" ::: "memory");
    prefetch_map(&maps.x); prefetch_map(&maps.wq); prefetch_map(&maps.k); prefetch_map(&maps.v);
  }
  if (warp == 9 && elect_one()) {
    mbar_init(bar_hw, 1); mbar_init(bar_hx, 1); mbar_init(bar_hx + 8, 1);
    asm volatile("fence.mbarrier_init.release.cluster;" ::: "memory");
    mbar_expect_tx(bar_hw, 32768);
    mbar_expect_tx(bar_hx, 16384);
    mbar_expect_tx(bar_hx + 8, 16384);
    const __nv_bfloat16* xs = P.x + (size_t)(rb * 128 + cj * 16) * DM;
    bulk_load(base + 2 * GST_BYTES, xs, 16384, bar_hx);
    if (!late) {
      tma2d(stage, &maps.wm, (b >> 1) * 32, rank * 512, bar_hw);
      tma2d(stage + 16384, &maps.wm, (b >> 1) * 32, rank * 512 + 256, bar_hw);
    }
    bulk_load(base + 3 * GST_BYTES, xs + 8 * DM, 16384, bar_hx + 8);
  }
  cluster_arrive();

  if (warp >= 8) {
    asm volatile("setmaxnreg.dec.sync.aligned.u32 40;");
    if (warp < 10) bar_arrive(1, 320);
    const uint32_t epoch = ld_relaxed(&g_epoch);
    cluster_wait();
    if (warp == 8) {
      const int kvrow = (cj >> 1) * SK + (SK - WIN);
      int wch = cj * 8 + rank * 2;
#pragma unroll 1
      for (int ps = 0; ps < 3; ps++) {
        const CUtensorMap* mw = ps == 2 ? &maps.wo : &maps.wq;
        const uint32_t xt = ps == 1 ? XT1 : XT2, wt = ps == 0 ? WT0 : (ps == 1 ? WT1 : WT2);
        const int nst = ps == 2 ? 32 : 16;
#pragma unroll 1
        for (int i = 0; i < nst; i++) {
          const uint32_t bf = gfull + (i & 3) * 8;
          const int kt = ps == 2 ? (((cj & 1) * 4 + ((i >> 1) & 3)) * 4 + (i >> 3)) * 2 + (i & 1) : (ps ? i : slice_of(i) + (b & 14)) & 15;
          const uint32_t wd = base + unit_of(wt, i & 3) + rank * UNIT, xd = base + unit_of(xt, i & 3);
          const uint8_t* xs = g_act + (uint32_t)(rb * 80 + (ps - 1) * 16 + kt) * UNIT;
          if (ps == 0 && i == HD) mbar_wait(bar_mod, 0);
          const bool xfirst = ps && i < 2;
          if (ps == 2 && i == 0) mbar_wait(bar_ofree + 24, 0);
          if (i == 0) fence_async();
          mbar_wait(gempty + (i & 3) * 8, ((i >> 2) & 1) ^ 1);
          if (elect_one()) {
            mbar_expect_tx(bf, ps ? GST_BYTES : 2 * UNIT);
            if (xfirst) bulk_load_stream(xd, xs, UNIT, bf);
          }
          if (ps && i < 4) mbar_wait(bempty + i * 8, 1);
          if (elect_one()) tma3d_mc<true>(wd, mw, 0, (i == 31 ? kt ^ (rank * 32) : kt) * 64, i == 31 ? cj * 2 : wch, bf);
          if (ps) {
            if (i == 16 || i == 24) { mbar_wait(bar_cnt + i - 16, 0); fence_async(); }
            if (i == RES0) mbar_wait(bar_res, 0);
            if (i == 2) mbar_wait(bar_ofree + (ps - 1) * 16, 0);
            if (elect_one()) {
              if (i == 31) bulk_load(xd, xs, UNIT, bf); else if (!xfirst) bulk_load_stream(xd, xs, UNIT, bf);
              mbar_arrive_pred(bar_go, i == GOST - 1);
              if (PG0 < 16) mbar_arrive_pred(bar_go2, ps == 1 && i == PG0);
              mbar_arrive_pred(bar_od, i == (ps == 1 ? ODS1 : ODS));
              if (i == RES0) mbar_expect_tx(bar_xres, 32768);
              if (i == RES0 || i == RES1) tma2d(base + OFF_RES + (i == RES1) * UNIT, &maps.x, cj * 128 + (i == RES1) * 64, rb * 128, bar_xres);
            }
          }
        }
        if (ps == 2) break;
        wch = ps ? ((wch >> 3) ^ rank) * 2 : wch + 4;
#pragma unroll 1
        for (int u = 0; u < 16; u++) {
          const bool isk = (u == 0) || ((u & 1) && u < 15);
          const int blk = (isk ? (u + 1) >> 1 : (u == 15 ? 7 : (u >> 1) - 1)) & 3;
          const uint32_t sl = base + unit_of(ps ? AT1 : AT0, u & 3) + rank * UNIT, bf = bfull + (u & 3) * 8;
          if (u < 4) mbar_wait(gempty + ((u + 1) >> 1) * 8, 1);
          mbar_wait(bempty + (u & 3) * 8, ((u >> 2) & 1) ^ 1);
          if (elect_one()) {
            mbar_arrive_pred(bar_go2, ps && u + 16 == PG0);
            mbar_expect_tx(bf, SLOT_BYTES);
            tma3d_mc<false>(sl, isk ? &maps.k : &maps.v, 0, kvrow + blk * 128, rank, bf);
          }
        }
      }
      if (elect_one()) mbar_expect_tx(bar_rx, UNIT);
      mbar_wait(bar_rel, 0);
      if (elect_one()) {
        bulk_load_stream(base + UNIT, g_act + (uint32_t)(rb * 80 + 16 + 63 - (cj & 1) * 32) * UNIT, UNIT, bar_rx);
      }
      if (b < NFFN) {
#pragma unroll 1
        for (int u = 0; u < 12; u++) {
          const uint32_t dst = base + unit_of(u < 4 ? FT_G : (u < 8 ? FT_U : FT_D), u & 3);
          if (elect_one()) mbar_expect_tx(bar_box + u * 8, UNIT);
          if (u == FB0 || u == FB1 || u == FB2) mbar_wait(bar_ring + (u == FB2 ? 16 : u == FB1 ? 8 : 0), 0);
          const int fp = u < FPB ? FPACE0 : FPACE;
          if (u >= fp) mbar_wait(bar_box + (u - fp) * 8, 0);
          if (elect_one()) {
            if (u < 8) tma2d(dst, u < 4 ? &maps.wg : &maps.wu, b * 32, (u & 3) * 256, bar_box + u * 8);
            else tma3d(dst, &maps.wd, 0, b * 32, (u - 8) * 4, bar_box + u * 8);
          }
        }
      }
    } else if (warp == 9) {
      const uint32_t target = 8 * (epoch + 1);
      uint32_t hmask = 0;
#pragma unroll 1
      for (int i = 0; i < 16; i++) {
        if (i == HDX) mbar_wait(bar_mod, 0);
        const int kt = (2 * cj + slice_of(i)) & 15;
        const uint32_t need = i == 15 ? 0xffffu : 1u << kt;
        if (i >= NRS && (hmask & need) != need) {
          uint32_t n = 0;
          do { hmask = __ballot_sync(0xffffffffu, ld_acquire(&g_cnt_h[rb * 32 + (lane & 15)]) == epoch + 1); watchdog(n); } while ((hmask & need) != need);
          PROF(1, lane == 0 && i == NRS, 26);
          fence_async();
        }
        mbar_wait(xempty + (i & 3) * 8, ((i >> 2) & 1) ^ 1);
        if (elect_one()) {
          mbar_expect_tx(xfull + (i & 3) * 8, UNIT);
          if (i < NRS) tma2d(base + (i & 3) * GST_BYTES, &maps.x, kt * 64, rb * 128, xfull + (i & 3) * 8);
          else bulk_load_stream(base + (i & 3) * GST_BYTES, g_act + (uint32_t)(rb * 80 + kt) * UNIT, UNIT, xfull + (i & 3) * 8);
        }
      }
      prefetch_map(&maps.wo);
#pragma unroll 1
      for (int t = 0; t < 4; t++) {
        if (t & 1) mbar_wait(bar_od, t >> 1);
#pragma unroll 1
        for (int p = 0; p < 32768 / OPS; p++) {
          const uint32_t w = p / (16384 / OPS), c = (p / (8192 / OPS)) & 1, off = w * 8192 + (p % (8192 / OPS)) * OPS;
          mbar_wait(bar_ofull + (t & 1) * 16 + w * 8, t >> 1);
          if (elect_one()) {
            bulk_store(g_act + (uint32_t)(rb * 80 + 16 + (cj * 4 + t) * 2 + c) * UNIT + off, base + unit_of(QT, 2 * t + c) + off, OPS);
            asm volatile("cp.async.bulk.commit_group;" ::: "memory");
            asm volatile("cp.async.bulk.wait_group.read %0;" ::"n"(OFL) : "memory");
          }
        }
        if (elect_one()) {
          asm volatile("cp.async.bulk.wait_group.read 0;" ::: "memory");
          mbar_arrive(t < 3 ? bar_ofree + t * 8 : bar_res);
          asm volatile("cp.async.bulk.wait_group 0;" ::: "memory");
          fence_async();
          red_release(&g_cnt_o[((rb * 4 + t) * 2 + (cj >> 2)) * 32], 2);
        }
        if (t) {
          wait_counter(&g_cnt_o[(rb * 8 + 2 * t + (cj & 1)) * 32], target);
          if (t & 1) wait_counter(&g_cnt_o[(rb * 8 + (t == 1 ? cj & 1 : 7 - (cj & 1))) * 32], target);
          if (elect_one()) mbar_arrive(t == 1 ? bar_ofree + 24 : bar_cnt + t * 8 - 16);
        }
      }
      PROF(2, lane == 0, 27);
      const uint32_t tag = epoch % 3 + 1;
      const uint32_t* inbox = g_cand + (lane & 15);
      mbar_wait(bar_ring + 16, 0);
      uint32_t c0 = ld_relaxed(inbox), n = 0;
#define CAND_STEP(cv)                                                                                        \
      {                                                                                                      \
        const bool valid = (cv & 3u) == tag, all = __all_sync(0xffffffffu, valid);                           \
        const uint32_t best = __reduce_max_sync(0xffffffffu, valid ? cv : 0u);                               \
        const uint32_t blk = __ffs(__ballot_sync(0xffffffffu, cv == best)) - 1;                              \
        if (best) sts2(par + PAR_CONST + 56, best, (blk << 7 | (~best >> 2 & 127)) | (all ? 0x1800 : 0x800)); \
        if (all) break;                                                                                      \
        cv = ld_relaxed(inbox);                                                                              \
      }
      while (true) { CAND_STEP(c0) watchdog(n); }
    } else {
      const int t2 = tid - 320;
      if (late && warp == 10) {
        mbar_wait(bar_hx, 0);
        if (elect_one()) {
          tma2d(stage, &maps.wm, (b >> 1) * 32, rank * 512, bar_hw);
          tma2d(stage + 16384, &maps.wm, (b >> 1) * 32, rank * 512 + 256, bar_hw);
        }
      }
      {
        const uint32_t tag = epoch % 3 + 1;
        mbar_wait(bar_hx + 8, 0);
        mbar_wait(bar_hw, 0);
        __nanosleep(late ? OSL2 : OSL);
        {
          const uint32_t t7 = (warp & 1) * 64 + (lane >> 4) * 32 + 16 + (lane & 15);
          const uint32_t* pm = g_modp + ((cj * 128 + t7 * 4) & (DM - 1));
          uint4 m0, m1, m2, m3;
          uint32_t n = 0;
          do {
            m0 = ld_relaxed4(pm); m1 = ld_relaxed4(pm + 2 * DM); m2 = ld_relaxed4(pm + DM); m3 = ld_relaxed4(pm + 3 * DM);
            watchdog(n);
          } while (!__all_sync(0xffffffffu, tag_ok(m0, tag) && tag_ok(m1, tag) && tag_ok(m2, tag) && tag_ok(m3, tag)));
          write_table(par, false, t7, m0, m1);
          write_table(par, true, t7, m2, m3);
          mbar_arrive(bar_mod2);
        }
      }
      mbar_wait(bar_hpub + (warp & 1) * 8, 0);
      PROF(1, t2 == 0, 24);
#pragma unroll 1
      for (int c = 0; c < 8; c++) {
        const uint32_t off = (warp & 1) * UNIT + c * 2048 + lane * 16;
        uint8_t* dst = g_act + (uint32_t)(rb * 80 + cj * 2) * UNIT + off;
        const uint4 v0 = lds4(stage + off), v1 = lds4(stage + off + 512), v2 = lds4(stage + off + 1024), v3 = lds4(stage + off + 1536);
        stg4(dst, v0); stg4(dst + 512, v1); stg4(dst + 1024, v2); stg4(dst + 1536, v3);
      }
      __syncwarp();
      PROF(1, t2 == 0, 15);
      if (lane == 0) {
        mbar_arrive(bar_pread);
        red_release(&g_cnt_h[rb * 32 + cj * 2 + (warp & 1)], 1);
        PROF(1, t2 == 0, 25);
        prefetch_map(&maps.wg); prefetch_map(&maps.wu); prefetch_map(&maps.wd); prefetch_map(&maps.out);
      }
      __syncwarp();
      if (b < NFFN) {
        mbar_wait(bar_go2, 0);
        const __nv_bfloat16* pg = ((b & 1) ? P.w_up : P.w_gate) + (b >> 1) * 64 + (size_t)t2 * FF;
        const __nv_bfloat16* pd = P.w_down + (size_t)b * 32768 + t2 * 64;
        PROF(2, t2 == 0, 13);
#pragma unroll 1
        for (int i = 0; i < WN; i += WB) {
          uint32_t v[WB];
#pragma unroll
          for (int u = 0; u < WB; u++) {
            const int k = i + u;
            asm volatile("ld.global.cg.L2::128B.u32 %0, [%1];" : "=r"(v[u]) : "l"(k < 16 ? pg + (size_t)k * 64 * FF : pd + (k - 16) * 4096));
          }
#pragma unroll
          for (int u = 1; u < WB; u++) v[0] ^= v[u];
          sts1(par + PAR_SINK + t2 * 4, v[0]);
        }
        PROF(2, t2 == 0, 14);
      }
      const uint32_t tag = epoch % 3 + 1;
      mbar_wait(bar_go, 0);
      bar_sync(4, 64);
      if (warp == 10) {
        const uint32_t* src = g_mod + 2 * DM + cj * 128 + lane * 4;
        const uint2 wr = *reinterpret_cast<const uint2*>(P.w_r + cj * 128 + lane * 4);
        uint4 vga, vsb, vcb, vgb;
        uint32_t n = 0;
        do {
          vga = ld_relaxed4(src); vsb = ld_relaxed4(src + DM); vcb = ld_relaxed4(src + 2 * DM); vgb = ld_relaxed4(src + 3 * DM);
          watchdog(n);
        } while (!__all_sync(0xffffffffu, tag_ok(vga, tag) && tag_ok(vsb, tag) && tag_ok(vcb, tag) && tag_ok(vgb, tag)));
        const float c0 = rbf(1.f + bf_hi(vcb.x)), c1 = rbf(1.f + bf_hi(vcb.y)), c2 = rbf(1.f + bf_hi(vcb.z)), c3 = rbf(1.f + bf_hi(vcb.w));
        const float a0 = c0 * bf_lo(wr.x), a1 = c1 * bf_hi(wr.x), a2 = c2 * bf_lo(wr.y), a3 = c3 * bf_hi(wr.y);
        const uint32_t h0 = pack_bf(a0, a1), h1 = pack_bf(a2, a3);
        const uint32_t t1 = par + PAR_T1 + (lane >> 2) * 64 + (lane & 1) * 32 + (lane & 2) * 2;
        sts1(t1, h0); sts1(t1 + 8, pack_bf(a0 - bf_lo(h0), a1 - bf_hi(h0)));
        sts1(t1 + 16, h1); sts1(t1 + 24, pack_bf(a2 - bf_lo(h1), a3 - bf_hi(h1)));
        const uint32_t tg = par + PAR_SINK + (lane >> 3) * 64 + (lane & 1) * 32 + (lane & 6) * 2;
        sts1(tg, __byte_perm(vga.x, vga.y, 0x7632)); sts1(tg + 16, __byte_perm(vga.z, vga.w, 0x7632));
        sts4(par + PAR_T2 + lane * 32, make_uint4(pack_bf(c0, c1), __byte_perm(vsb.x, vsb.y, 0x7632), __byte_perm(vgb.x, vgb.y, 0x7632), __byte_perm(vga.x, vga.y, 0x7632)));
        sts4(par + PAR_T2 + lane * 32 + 16, make_uint4(pack_bf(c2, c3), __byte_perm(vsb.z, vsb.w, 0x7632), __byte_perm(vgb.z, vgb.w, 0x7632), __byte_perm(vga.z, vga.w, 0x7632)));
      } else {
        const uint4 g = poll4((lane & 2) ? g_mod + 8 - (lane & 1) * 4 : g_mod + 5 * DM + b * 8 + (lane & 1) * 4, tag);
        sts1(par + PAR_CONST + 60, 0);
        if (lane < 2) sts4(par + PAR_CONST + 16 + lane * 16, g);
        else if (lane < 4) sts2(par + PAR_CONST + (lane - 2) * 8, __float_as_uint(untag_sum(g.x, g.y) + untag_sum(g.z, g.w)), epoch);
      }
      __syncwarp();
#pragma unroll 4
      for (int q = 0; q < 32; q++) st_b128(g_xch + ((size_t)b * 8 * 256 + q * 64 + t2) * 4, (epoch & 1) << 16, 0, 0, 0);
      for (int q = 0; q < 2; q++) st_relaxed4(g_stats + ((size_t)cj * SEQ + rb * 128 + q * 64 + t2) * 4, 0, 0, 0, 0);
      if (b < NFFN)
        for (int q = 0; q < 4; q++) st_relaxed4(g_ypart + ((size_t)(q * 32 + (t2 >> 1)) * NFFN + b) * 8 + (t2 & 1) * 4, 0, 0, 0, 0);
      st_relaxed4(g_row + rb * 2 * DM + (t2 >> 5) * DM + cj * 128 + (t2 & 31) * 4, 0, 0, 0, 0);
      __threadfence();
      mbar_arrive(bar_par);
      mbar_wait(bar_gate, 0);
      uint32_t have = 0, n = 0;
      while (true) {
        const uint32_t st = lds1(par + PAR_CONST + 60) >> 7;
        if ((st & 31) != have) {
          const uint32_t* hsrc = g_row + (st & 15) * 2 * DM + t2 * 4;
          uint4 hv[4];
          bool ok = true;
#pragma unroll
          for (int i = 0; i < 4; i++) hv[i] = ld_pairs(hsrc + i * 256);
#pragma unroll
          for (int i = 0; i < 4; i++) {
            sts2(base + ((FT_G >> i * 4) & 15) * UNIT + (warp & 1) * 8192 + 256 + lane * 8, hv[i].x, hv[i].z);
            ok = ok && hv[i].y == tag && hv[i].w == tag;
          }
          have = __all_sync(0xffffffffu, ok) ? st & 31 : 0;
        }
        if ((st ^ have) == 32) break;
        watchdog(n);
      }
      mbar_arrive(bar_sel);
    }
    __syncwarp();
    cluster_arrive();
    {
      const uint32_t tag = epoch % 3 + 1, t3 = tid - 256;
      mbar_wait(bar_win, 0);
      uint2 win = lds2(par + PAR_CONST + 56);
      win.y &= 0x7ff;
      const uint32_t* fsrc = g_row + (win.y >> 7) * 2 * DM + (b >> 1) * 16 + (t3 & 3) * 4 + (b & 1) * 2;
      const uint32_t* ysrc = g_ypart + (size_t)b * NFFN * 8 + min(t3, NFFN - 1) * 4;
      uint2 fh = ld_pair(fsrc), fx = ld_pair(fsrc + DM);
      if (PSL) __nanosleep(PSL);
      uint4 ya = ld_relaxed4(ysrc), yb = ld_relaxed4(ysrc + NFFN * 4);
      const float rwin = __uint_as_float(((int)win.x < 0 ? win.x & 0x7fffffffu : ~win.x) & ~0x1ffu);
      const float rs = rbf(rcp(1.f + __expf(-rbf(rwin))));
      uint32_t n = 0;
      while (__any_sync(0xffffffffu, fh.y != tag || fx.y != tag)) { fh = ld_pair(fsrc); fx = ld_pair(fsrc + DM); watchdog(n); }
      while (!__all_sync(0xffffffffu, tag_ok(ya, tag) && tag_ok(yb, tag))) {
        if (!tag_ok(ya, tag)) ya = ld_relaxed4(ysrc);
        if (!tag_ok(yb, tag)) yb = ld_relaxed4(ysrc + NFFN * 4);
        watchdog(n);
      }
      __syncwarp();
      PROF(8, t3 == 0, 5);
      float y0 = untag_sum(ya.x, yb.x), y1 = untag_sum(ya.y, yb.y), y2 = untag_sum(ya.z, yb.z), y3 = untag_sum(ya.w, yb.w);
      const bool u1 = lane & 2, u2 = lane & 4;
      y0 = (u1 ? y2 : y0) + __shfl_xor_sync(0xffffffffu, u1 ? y0 : y2, 2);
      y1 = (u1 ? y3 : y1) + __shfl_xor_sync(0xffffffffu, u1 ? y1 : y3, 2);
      y0 = (u2 ? y1 : y0) + __shfl_xor_sync(0xffffffffu, u2 ? y0 : y1, 4);
      y0 += __shfl_xor_sync(0xffffffffu, y0, 8);
      if (!(lane & 8)) sts1(par + PAR_RED + 64 + (t3 >> 4) * 32 + ((lane & 1) * 4 + (lane & 2) + ((lane >> 2) & 1)) * 4, __float_as_uint(y0));
      bar_sync(4, 128);
      if (t3 < 4) {
        y0 = 0.f; y1 = 0.f;
#pragma unroll
        for (int w4 = 0; w4 < 7; w4++) {
          const uint2 v = lds2(par + PAR_RED + 64 + w4 * 32 + t3 * 8);
          y0 += __uint_as_float(v.x); y1 += __uint_as_float(v.y);
        }
        const uint2 gv = lds2(par + PAR_CONST + 16 + t3 * 8);
        const uint32_t upd = hmul2(pack_bf(y0, y1), pack_bf(rs, rs));
        *reinterpret_cast<uint32_t*>(P.out + (size_t)win.y * DM + b * 8 + t3 * 2) =
            hadd2(fx.x, hmul2(__byte_perm(gv.x, gv.y, 0x7632), hadd2(fh.x, upd)));
        if (b == 0 && t3 == 0) st_relaxed(&g_epoch, epoch + 1);
      }
      PROF(31, t3 == 0, 36);
    }
    cluster_wait();
  } else {
    const int wg = warp >> 2;

    uint32_t tag;
    {
      uint32_t* const pmod = g_modp + rank * 2 * DM + (b >> 1) * 32 + lane;
      uint32_t* const pln = g_ln1 + (rb * 128 + cj * 16 + warp) * 4;
      uint32_t sc[8];
#pragma unroll
      for (int k = 0; k < 8; k++) sc[k] = ldg_nc1(P.c + rank * 512 + warp * 64 + k * 8 + (lane & 3) * 2);
      const uint32_t epoch = ld_relaxed(&g_epoch);
      if (warp == 0) st_relaxed(pmod, 0);
      if (lane == 0) { st_b128(pln, 0, 0, 0, 0); st_b128(pln + 32, 0, 0, 0, 0); }
      asm volatile("setmaxnreg.inc.sync.aligned.u32 232;");
      bar_sync(1, 320);
#pragma unroll
      for (int k = 0; k < 8; k++) sc[k] = pack_bf(silu_f(bf_lo(sc[k])), silu_f(bf_hi(sc[k])));
      keep(sc);
      tag = epoch % 3 + 1;
#pragma unroll
      for (int part = 0; part < 4; part++) {
        if (!(part & 1)) {
          const uint32_t xa = base + (2 + part / 2) * GST_BYTES + warp * 2048 + lane * 16;
          mbar_wait(bar_hx + part * 4, 0);
          float s0 = 0.f, s1 = 0.f, q0 = 0.f, q1 = 0.f;
#pragma unroll
          for (int q = 0; q < 4; q++) {
            const uint4 xv = lds4(xa + q * 512);
            const uint32_t u[4] = {xv.x, xv.y, xv.z, xv.w};
#pragma unroll
            for (int e = 0; e < 4; e++) { const float lo = bf_lo(u[e]), hi = bf_hi(u[e]); s0 += lo; s1 += hi; q0 += lo * lo; q1 += hi * hi; }
          }
          s0 += s1; q0 += q1;
#pragma unroll
          for (int o = 16; o > 0; o >>= 1) { s0 += __shfl_xor_sync(0xffffffffu, s0, o); q0 += __shfl_xor_sync(0xffffffffu, q0, o); }
          const float mean = s0 * (1.f / DM);
          float mb, sd;
          ln_scalars(mean, fmaxf(q0 * (1.f / DM) - mean * mean, 0.f), mb, sd);
          uint32_t ih, il;
          split_inv(sd, ih, il);
          if (lane == 0) st_b128(pln + part * 16, pack_bf(mb, mb), ih, il, tag);
          PROF(1, tid == 0 && part == 2, 4);
        } else if (late == (part == 3)) {
          const uint32_t fr = (lane & 7) + (lane >> 4) * 8, tq = lane & 3;
          const uint32_t wa = stage + warp * 4096 + fr * 64 + ((((lane >> 3) & 1) ^ ((fr >> 1) & 3)) << 4);
          float d0[4] = {0.f, 0.f, 0.f, 0.f}, d1[4] = {0.f, 0.f, 0.f, 0.f};
          mbar_wait(bar_hw, 0);
#pragma unroll
          for (int ks = 0; ks < 4; ks++) {
            uint32_t w[8];
            ldmatrix4t(wa + ks * 1024, w[0], w[1], w[2], w[3]);
            ldmatrix4t((wa ^ 32) + ks * 1024, w[4], w[5], w[6], w[7]);
            mma16816(d0, w[0], w[1], w[2], w[3], sc[2 * ks], sc[2 * ks + 1]);
            mma16816(d1, w[4], w[5], w[6], w[7], sc[2 * ks], sc[2 * ks + 1]);
          }
          sts1(base + 2 * GST_BYTES + warp * 2048 + (tq * 8 + (lane >> 2)) * 4, __float_as_uint((tq & 2) ? ((tq & 1) ? d1[2] : d1[0]) : ((tq & 1) ? d0[2] : d0[0])));
          bar_sync(1, 256);
          if (warp == 0) {
            float s = 0.f;
#pragma unroll
            for (int w8 = 0; w8 < 8; w8++) s += __uint_as_float(lds1(base + 2 * GST_BYTES + w8 * 2048 + lane * 4));
            st_relaxed(pmod, (__float_as_uint(s) & ~3u) | tag);
          }
          PROF(1, tid == 0, 3);
        }
      }
      cluster_wait();
      if (wg == 1) bar_arrive(2, 256);
    }

    float f0 = 0.f, f1 = 0.f;
    const uint32_t rempty = lane < 2 ? mapa(bempty, lane & 1) : 0;
    constexpr uint32_t GE = NSLOT * 8 + 32;
    float o[64], s[64];
#pragma unroll 1
    for (int ps = 0; ps < 3; ps++) {
      {
        const uint32_t xt = ps == 1 ? XT1 : XT2, wt = ps == 1 ? WT1 : WT2;
        const int nst = ps == 2 ? 28 : 14;
        if (ps == 0) {
          float ga[64], gb[64];
#pragma unroll
          for (int i = 0; i < 64; i++) { ga[i] = 0.f; gb[i] = 0.f; }
          uint32_t a[2][16];
          const uint32_t l = fresh_lane();
          uint32_t fa[4];
#pragma unroll
          for (int kk = 0; kk < 4; kk++) fa[kk] = (base + wg * 8192 + frag_offset(warp)) ^ (kk * 32);
          const uint32_t mt = par + (l & 3) * 16;
          auto fetch = [&](int i, uint32_t (&f)[16], uint32_t z) {
            mbar_wait(xfull + (i & 3) * 8, i >> 2);
#pragma unroll
            for (int kk = 0; kk < 4; kk++) ldmatrix4(fa[kk] + (i & 3) * GST_BYTES + z, f[4 * kk], f[4 * kk + 1], f[4 * kk + 2], f[4 * kk + 3]);
          };
          const bool oddw = warp & 2;
          uint4 r0, r1;
          {
            const uint32_t t7 = (warp & 1) * 64 + (l >> 4) * 32 + (l & 15);
            const uint32_t* pm = g_modp + wg * DM + ((cj * 128 + t7 * 4) & (DM - 1));
            const uint32_t* pr = g_ln1 + (rb * 128 + warp * 16 + (l >> 2)) * 4;
            uint4 m0 = make_uint4(tag, tag, tag, tag), m1 = m0;
            if (!oddw) { m0 = ld_relaxed4(pm); m1 = ld_relaxed4(pm + 2 * DM); }
            r0 = ld_b128(pr); r1 = ld_b128(pr + 32);
            fetch(0, a[0], 0); fetch(1, a[1], 0);
            uint32_t n = 0;
            bool written = false;
#pragma unroll 1
            while (true) {
              uint32_t miss;
              asm volatile("{ .reg .pred p0, p1, p2, p3; .reg .b32 t, u;\n"
                           "lop3.b32 t, %1, %2, %19, 0x7e; lop3.b32 u, %3, %4, %19, 0x7e; or.b32 t, t, u; and.b32 t, t, 3; setp.ne.u32 p0, t, 0;\n"
                           "lop3.b32 t, %5, %6, %19, 0x7e; lop3.b32 u, %7, %8, %19, 0x7e; or.b32 t, t, u; and.b32 t, t, 3; setp.ne.u32 p1, t, 0;\n"
                           "setp.ne.u32 p2, %12, %19; setp.ne.u32 p3, %16, %19;\n"
                           "@p0 ld.relaxed.gpu.global.v4.u32 {%1, %2, %3, %4}, [%17];\n"
                           "@p1 ld.relaxed.gpu.global.v4.u32 {%5, %6, %7, %8}, [%17 + 8192];\n"
                           "@p2 ld.relaxed.gpu.global.v4.u32 {%9, %10, %11, %12}, [%18];\n"
                           "@p3 ld.relaxed.gpu.global.v4.u32 {%13, %14, %15, %16}, [%18 + 128];\n"
                           "or.pred p0, p0, p1; or.pred p2, p2, p3; vote.sync.any.pred p0, p0, 0xffffffff; vote.sync.any.pred p2, p2, 0xffffffff;\n"
                           "selp.u32 t, 1, 0, p0; selp.u32 u, 2, 0, p2; or.b32 %0, t, u; }"
                           : "=r"(miss), "+r"(m0.x), "+r"(m0.y), "+r"(m0.z), "+r"(m0.w), "+r"(m1.x), "+r"(m1.y), "+r"(m1.z), "+r"(m1.w),
                             "+r"(r0.x), "+r"(r0.y), "+r"(r0.z), "+r"(r0.w), "+r"(r1.x), "+r"(r1.y), "+r"(r1.z), "+r"(r1.w)
                           : "l"(pm), "l"(pr), "r"(tag) : "memory");
              if (!(miss & 1) && !written) {
                written = true;
                if (!oddw) write_table(par, wg, t7, m0, m1);
                mbar_arrive(bar_mod);
              }
              if (!miss) break;
              watchdog(n);
            }
          }
          const uint32_t zero = r0.w ^ tag;
          auto normalize = [&](uint32_t (&f)[16]) {
#pragma unroll
            for (int k = 0; k < 16; k += 2) { f[k] = ln_norm(f[k], r0.x, r0.y, r0.z); f[k + 1] = ln_norm(f[k + 1], r1.x, r1.y, r1.z); }
          };
          auto modulate = [&](int i, uint32_t (&f)[16]) {
#pragma unroll
            for (int kk = 0; kk < 4; kk++) {
              const uint4 m = lds4(mt + slice_of(i) * 256 + kk * 64);
              f[4 * kk] = MODUL(f[4 * kk], m.x, m.z); f[4 * kk + 1] = MODUL(f[4 * kk + 1], m.x, m.z);
              f[4 * kk + 2] = MODUL(f[4 * kk + 2], m.y, m.w); f[4 * kk + 3] = MODUL(f[4 * kk + 3], m.y, m.w);
            }
            keep(f);
            mbar_arrive_pred(xempty + (i & 3) * 8, l == 0);
          };
          auto publish = [&](int u, uint32_t (&f)[16]) {
#pragma unroll
            for (int kk = 0; kk < 4; kk++) stmatrix4(fa[kk] + OFF_STAGE + u * UNIT, f[4 * kk], f[4 * kk + 1], f[4 * kk + 2], f[4 * kk + 3]);
            __syncwarp();
            mbar_arrive_pred(bar_hpub + u * 8, l == 0);
          };
          auto multiply = [&](int i, uint32_t (&f)[16]) {
            mbar_wait(gfull + (i & 3) * 8, i >> 2);
            const uint64_t db = make_desc(base + (i & 3) * GST_BYTES + UNIT, 8192, 1024);
            wg_fence();
#pragma unroll
            for (int kk = 0; kk < 4; kk++) mma256_rs(ga, gb, f[4 * kk], f[4 * kk + 1], f[4 * kk + 2], f[4 * kk + 3], db + kk * 128);
            wg_commit();
          };
          auto next = [&](int i, uint32_t (&f)[16]) {
            wg_wait<1>();
            mbar_arrive_cl(rempty, GE + ((i + 2) & 3) * 8);
            uint32_t z = zero;
#pragma unroll
            for (int k = 0; k < 16; k += 2) asm volatile("lop3.b32 %0, %1, %2, %0, 0xA8;" : "+r"(z) : "r"(f[k]), "r"(f[k + 1]));
            fetch(i, f, z);
            normalize(f);
            if (i == 2) { keep(f); mbar_wait(bar_mod2, 0); }
            modulate(i, f); multiply(i, f);
          };
          normalize(a[0]); normalize(a[1]);
          keep(a[0]); keep(a[1]);
          mbar_wait(bar_mod, 0);
          PROF(1, tid == 0, 2);
          modulate(0, a[0]); multiply(0, a[0]); publish(0, a[0]);
          modulate(1, a[1]); multiply(1, a[1]);
#pragma unroll 1
          for (int i = 2; i < NRS; i += 2) {
            next(i, a[0]);
            if (i == 2) publish(1, a[0]);
            next(i + 1, a[1]);
          }
          wg_wait<1>();
          mbar_arrive_cl(rempty, GE + ((NRS + 2) & 3) * 8);
#pragma unroll 1
          for (int i = NRS; i < 14; i++) {
            mbar_wait(xfull + (i & 3) * 8, (i >> 2) & 1);
            mbar_wait(gfull + (i & 3) * 8, (i >> 2) & 1);
            const uint32_t xa = base + (i & 3) * GST_BYTES;
            const uint64_t da = make_desc(xa + wg * 8192, 16, 1024), db = make_desc(xa + UNIT, 8192, 1024);
            if (i == 13) bar_sync(2 + wg, 256);
            wg_fence();
#pragma unroll
            for (int kk = 0; kk < 4; kk++) mma256_ss(ga, gb, da + kk * 2, db + kk * 128, 1);
            wg_commit();
            if (i == 13) bar_arrive(3 - wg, 256);
            wg_wait<1>();
            uint32_t z = zero;
#pragma unroll
            for (int k = 0; k < 16; k += 2) asm volatile("lop3.b32 %0, %1, %2, %0, 0xA8;" : "+r"(z) : "r"(a[1][k]), "r"(a[1][k + 1]));
            mbar_arrive_cl(rempty, GE + ((i + 3) & 3) * 8 + z);
            mbar_arrive_pred(xempty + ((i + 3) & 3) * 8, l == 0 && i != NRS);
          }
          mbar_wait(xfull + 16, 1);
          wg_wait<0>();
          keep(ga); keep(gb);
#pragma unroll
          for (int i = 0; i < 64; i++) {
            asm volatile("mov.b32 %0, %1;" : "=f"(s[i]) : "f"(ga[i]));
            asm volatile("mov.b32 %0, %1;" : "=f"(o[i]) : "f"(gb[i]));
          }
        } else {
          float ga[64], gb[64];
#pragma unroll
          for (int i = 0; i < 64; i++) {
            asm volatile("mov.b32 %0, %1;" : "=f"(ga[i]) : "f"(s[i]));
            asm volatile("mov.b32 %0, %1;" : "=f"(gb[i]) : "f"(o[i]));
          }
#pragma unroll 1
          for (int i = 0; i < nst; i++) {
            mbar_wait(gfull + (i & 3) * 8, (i >> 2) & 1);
            const uint64_t da = make_desc(base + unit_of(xt, i & 3) + wg * 8192, 16, 1024), db = make_desc(base + unit_of(wt, i & 3), 8192, 1024);
            if (i == nst - 1) bar_sync(2 + wg, 256);
            wg_fence();
#pragma unroll
            for (int kk = 0; kk < 4; kk++) mma256_ss(ga, gb, da + kk * 2, db + kk * 128, kk ? 1 : i);
            wg_commit();
            if (i == nst - 1) bar_arrive(3 - wg, 256);
            wg_wait<1>();
            mbar_arrive_cl(rempty, GE + ((i + 3) & 3) * 8, i != 0);
            PROF(4, tid == 0 && (i & 3) == 0, 40 + (ps - 1) * 4 + i / 4);
          }
          wg_wait<0>();
          keep(ga); keep(gb);
#pragma unroll
          for (int i = 0; i < 64; i++) {
            asm volatile("mov.b32 %0, %1;" : "=f"(s[i]) : "f"(ga[i]));
            asm volatile("mov.b32 %0, %1;" : "=f"(o[i]) : "f"(gb[i]));
          }
        }
        mbar_arrive_cl(rempty, GE + (ps == 2 ? 24 : 8));
        if (ps == 2) break;
      }
      const uint32_t qw = base + wg * 8192, qt = QT >> (16 * ps), at = ps ? AT1 : AT0;
      uint32_t pa[32], pb[32];
      const uint32_t wt = ps ? WT1 : WT0;
      {
        const uint64_t da0 = make_desc(qw + unit_of(qt, 2), 16, 1024), da1 = make_desc(qw + unit_of(qt, 3), 16, 1024);
        const uint64_t db0 = make_desc(base + unit_of(wt, 2), 8192, 1024), db1 = make_desc(base + unit_of(wt, 3), 8192, 1024);
        mbar_wait(gfull + 16, 1);
        bar_sync(2 + wg, 256);
        wg_fence();
#pragma unroll
        for (int kk = 0; kk < 4; kk++) mma_ss<1>(s, da0 + kk * 2, db0 + kk * 128, 1);
        wg_commit();
        mbar_wait(xfull + 24, 1);
        mbar_wait(gfull + 24, 1);
        wg_fence();
#pragma unroll
        for (int kk = 0; kk < 4; kk++) mma_ss<1>(s, da1 + kk * 2, db1 + kk * 128, 1);
        wg_commit();
        bar_arrive(3 - wg, 256);
        mbar_wait(ps == 0 ? bar_pread : bar_ofree + 8, 0);
        wg_wait<0>();
        keep(s);
        PROF(2, tid == 0, 8 + ps * 8);
        pack_p(s, pb);
#pragma unroll
        for (int i = 0; i < 4; i++) stmatrix4((qw + unit_of(qt, 0) + frag_offset(warp)) ^ (i << 5), pb[4 * i], pb[4 * i + 1], pb[4 * i + 2], pb[4 * i + 3]);
        keep(pb);
      }
      auto first_batch = [&]() {
        const uint64_t da0 = make_desc(qw + unit_of(qt, 2), 16, 1024), da1 = make_desc(qw + unit_of(qt, 3), 16, 1024);
        const uint64_t db0 = make_desc(base + unit_of(wt, 2) + UNIT, 8192, 1024), db1 = make_desc(base + unit_of(wt, 3) + UNIT, 8192, 1024);
        bar_sync(2 + wg, 256);
        wg_fence();
#pragma unroll
        for (int kk = 0; kk < 8; kk++) mma_ss<1>(o, (kk < 4 ? da0 : da1) + (kk & 3) * 2, (kk < 4 ? db0 : db1) + (kk & 3) * 128, 1);
        wg_commit();
        mbar_wait(bfull, 0);
        wg_fence();
        const uint64_t dk = make_desc(base + unit_of(at, 0), 16, 1024);
#pragma unroll
        for (int kk = 0; kk < 8; kk++) mma_rs<0>(s, pb[4 * kk], pb[4 * kk + 1], pb[4 * kk + 2], pb[4 * kk + 3], dk + (kk >> 2) * 1024 + (kk & 3) * 2, kk != 0);
        wg_commit();
        bar_arrive(3 - wg, 256);
#pragma unroll
        for (int i = 4; i < 8; i++) stmatrix4((qw + unit_of(qt, 1) + frag_offset(warp)) ^ ((i & 3) << 5), pb[4 * i], pb[4 * i + 1], pb[4 * i + 2], pb[4 * i + 3]);
        wg_wait<1>();
        keep(o);
        mbar_arrive_cl(rempty, GE + 16);
        mbar_arrive_cl(rempty, GE + 24);
        store_chunk<0>(o, qw + unit_of(qt, 2) + frag_offset(warp));
        store_chunk<1>(o, qw + unit_of(qt, 3) + frag_offset(warp));
        wg_wait<0>();
        keep(s);
        mbar_arrive_cl(rempty, 0);
        PROF(4, tid == 0 && ps == 1, 61);
      };
      float l0 = 0.f, l1 = 0.f, i0, i1;
      auto softmax = [&](auto odd_c, const int j, uint32_t (&pw)[32]) {
        constexpr bool ODD = decltype(odd_c)::value;
        const bool first = !ODD && (j & 2) == 0;
        float a0, a1;
        if (!ODD) { i0 = 0.f; i1 = 0.f; }
        if (!ODD && j == 4) { i0 = inv_quad_sum(l0); i1 = inv_quad_sum(l1); l0 = 0.f; l1 = 0.f; }
        bool redo = !ODD && (j | ps) == 0;
        while (true) {
          if (redo) {
            float m0 = fmaxf(s[0], s[1]), m1 = fmaxf(s[2], s[3]);
#pragma unroll
            for (int i = 1; i < 16; i++) { m0 = fmaxf(m0, fmaxf(s[4 * i], s[4 * i + 1])); m1 = fmaxf(m1, fmaxf(s[4 * i + 2], s[4 * i + 3])); }
            m0 = fmaxf(m0, __shfl_xor_sync(0xffffffffu, m0, 1)); m1 = fmaxf(m1, __shfl_xor_sync(0xffffffffu, m1, 1));
            m0 = fmaxf(m0, __shfl_xor_sync(0xffffffffu, m0, 2)); m1 = fmaxf(m1, __shfl_xor_sync(0xffffffffu, m1, 2));
            m0 *= SCL2; m1 *= SCL2;
            if (!first) {
              m0 = fmaxf(m0, f0); m1 = fmaxf(m1, f1);
              const float c0 = ex2(f0 - m0), c1 = ex2(f1 - m1);
              l0 *= c0; l1 *= c1;
              wg_wait<0>();
              keep(o);
#pragma unroll
              for (int i = 0; i < 16; i++) { o[4 * i] *= c0; o[4 * i + 1] *= c0; o[4 * i + 2] *= c1; o[4 * i + 3] *= c1; }
            }
            f0 = m0; f1 = m1;
          }
          float b0 = 0.f, b1 = 0.f;
          a0 = 0.f; a1 = 0.f;
#pragma unroll
          for (int i = 0; i < 16; i++) {
            const float e0 = ex2(fmaf(s[4 * i], SCL2, -f0)), e1 = ex2(fmaf(s[4 * i + 1], SCL2, -f0));
            const float e2 = ex2(fmaf(s[4 * i + 2], SCL2, -f1)), e3 = ex2(fmaf(s[4 * i + 3], SCL2, -f1));
            a0 += e0; b0 += e1; a1 += e2; b1 += e3;
            pw[2 * i] = pack_bf(e0, e1); pw[2 * i + 1] = pack_bf(e2, e3);
            if (i == VREL) {
#pragma unroll
              for (int k = 0; k < 2 * VREL + 2; k++) asm volatile("" : "+r"(pw[k])::"memory");
              mbar_wait(bar_mod, 0);
              wg_wait<0>();
              mbar_arrive_cl(rempty, ODD ? 16 : 0, !redo && (ODD || j));
#pragma unroll
              for (int k = 4 * VREL + 4; k < 64; k++) asm volatile("" : "+f"(s[k])::"memory");
            }
          }
          a0 += b0; a1 += b1;
          if (redo) break;
          redo = __any_sync(0xffffffffu, !(a0 + a1 < 0x1p90f));
          if (first) {
            uint32_t m0 = __ballot_sync(0xffffffffu, a0 > 0x1p-80f), m1 = __ballot_sync(0xffffffffu, a1 > 0x1p-80f);
            m0 |= m0 >> 1; m1 |= m1 >> 1; m0 |= m0 >> 2; m1 |= m1 >> 2;
            redo = redo || (m0 & m1 & 0x11111111u) != 0x11111111u;
          }
          if (!redo) break;
        }
        l0 += a0; l1 += a1;
        keep(pw);
        keep(o);
      };
      auto batch = [&](auto odd_c, const int j, uint32_t (&pw)[32]) {
        constexpr bool ODD = decltype(odd_c)::value;
        const uint32_t ph = (j >> 1) & 1;
        const bool so = !ODD && j == 4;
        if (so) store_chunk<0>(o, i0, i1, qw + unit_of(qt, 0) + frag_offset(warp));
        keep(o);
        if (j == (ODD ? 5 : 0)) { fence_async_smem(); if (ODD) mbar_arrive(bar_ofull + wg * 8); }
        mbar_wait(bfull + (ODD ? 24 : 8), ph);
        bar_sync(2 + wg, 256);
        const uint32_t qn = qt >> (j >= 3 ? 8 : 0);
        wg_fence();
        issue_qk(s, qw + unit_of(qn, 0), qw + unit_of(qn, 1), base + unit_of(at, ODD ? 3 : 1));
        wg_commit();
        mbar_wait(bfull + (ODD ? 0 : 16), ODD ? ph ^ 1 : ph);
        if (so) { store_chunk<1>(o, i0, i1, qw + unit_of(qt, 1) + frag_offset(warp)); keep(o); }
        wg_fence();
        issue_pv(o, pw, base + unit_of(at, ODD ? 0 : 2), ODD || (j & 2));
        wg_commit();
        bar_arrive(3 - wg, 256);
        wg_wait<1>();
        keep(s);
        mbar_arrive_cl(rempty, ODD ? 24 : 8);
        PROF(4, tid == 0 && ps == 1, 51 + j);
      };
#pragma unroll 1
      for (int j = 0; j < 8; j += 2) {
        if (j == 0) first_batch(); else batch(std::true_type{}, j - 1, pb);
        softmax(std::false_type{}, j, pa);
        batch(std::false_type{}, j, pa);
        softmax(std::true_type{}, j + 1, pb);
      }
      {
        mbar_wait(bfull + 24, 1);
        bar_sync(2 + wg, 256);
        wg_fence();
        issue_pv(o, pb, base + unit_of(at, 3), 1);
        wg_commit();
        bar_arrive(3 - wg, 256);
        i0 = inv_quad_sum(l0); i1 = inv_quad_sum(l1);
        wg_wait<0>();
        keep(o);
        mbar_arrive_cl(rempty, 24);
        store_chunk<0>(o, i0, i1, qw + unit_of(qt, 2) + frag_offset(warp));
        store_chunk<1>(o, i0, i1, qw + unit_of(qt, 3) + frag_offset(warp));
        fence_async_smem();
        mbar_arrive(bar_ofull + 16 + wg * 8);
      }
      PROF(2, tid == 0, 10 + ps * 8);
    }

    const int ln = fresh_lane(), g = ln >> 2, tq = ln & 3, ct = warp * 32 + ln;
    const bool lane0 = ln == 0;
    const int lrow0 = warp * 16 + g;
    const int grow0 = rb * 128 + lrow0;
    const uint32_t res = base + OFF_RES, trow = res + wg * 8192 + frag_offset(warp);
    uint32_t xr[32];
    uint4 sv[4], own;
    uint32_t* sp[4];
#pragma unroll
    for (int k = 0; k < 4; k++) sp[k] = g_stats + ((((tq >> 1) * 4 + k) ^ cj) * SEQ + grow0 + (tq & 1) * 8) * 4;
    {
      const uint64_t da = make_desc(base + wg * 8192, 16, 1024), db = make_desc(base, 8192, 1024);
      constexpr int U = UNIT / 16;
#define HALF_STAGE(acc, xu, wu) _Pragma("unroll") for (int kk = 0; kk < 4; kk++) mma_ss<1>(acc, da + (xu) * U + kk * 2, db + (wu) * U + kk * 128, 1)
      PROF(10, ct == PT, 19); STAMP(0);
      cluster_arrive();
      mbar_wait(gfull, 1);
      mbar_wait(gfull + 8, 1);
      bar_sync(2 + wg, 256);
      wg_fence();
      HALF_STAGE(o, 7, 1);
      HALF_STAGE(o, 8, 3);
      wg_commit();
      STAMP(16);
      mbar_wait(gfull + 16, 1);
      STAMP(17);
      wg_fence();
      HALF_STAGE(o, 6, 11);
      wg_commit();
      bar_arrive(3 - wg, 256);
      mbar_wait(bar_par, 0);
      uint32_t* xo = g_xch + ((size_t)b * 8 * 256 + ct) * 4;
      const uint32_t* xi = g_xch + ((size_t)(b ^ 2) * 8 * 256 + ct) * 4;
      const uint32_t par1 = (~lds1(par + PAR_CONST + 4) & 1) << 16;
      wg_wait<1>();
      mbar_arrive_pred(bar_rel, lane0);
      wg_wait<0>();
      keep(o);
      mbar_arrive_pred(bar_ring, lane0);
      PROF(8, ct == PT, 20); STAMP(1);
#define SEND(i) st_b128(xo + (i) * 1024, (pack_bf(o[8 * (i)], o[8 * (i) + 1]) & ~0x10000u) | par1, pack_bf(o[8 * (i) + 2], o[8 * (i) + 3]), \
                        pack_bf(o[8 * (i) + 4], o[8 * (i) + 5]), pack_bf(o[8 * (i) + 6], o[8 * (i) + 7]))
#pragma unroll
      for (int i = 0; i < NS1; i++) SEND(i);
      PROF(8, ct == PT, 21); STAMP(2);
      bar_sync(2 + wg, 256);
      wg_fence();
      HALF_STAGE(s, 7, 0);
      HALF_STAGE(s, 8, 2);
      HALF_STAGE(s, 6, 10);
      wg_commit();
      bar_arrive(3 - wg, 256);
      STAMP(18);
      mbar_wait(gfull + 24, 1);
#pragma unroll
      for (int i = NS1; i < 8; i++) SEND(i);
      uint4 v[8];
#pragma unroll
      for (int i = 0; i < LD1; i++) v[i] = ld_b128(xi + i * 1024);
      STAMP(19);
      mbar_wait(bar_xres, 0);
      wg_wait<0>();
      mbar_arrive_pred(bar_ring + 8, lane0);
      bar_sync(2 + wg, 256);
      STAMP(20);
#pragma unroll
      for (int i = LD1; i < LD2; i++) v[i] = ld_b128(xi + i * 1024);
      mbar_wait(bar_xres, 0);
      wg_fence();
      HALF_STAGE(s, 9, 4);
      wg_commit();
      mbar_wait(bar_rx, 0);
      wg_fence();
      HALF_STAGE(s, 1, 5);
      wg_commit();
      bar_arrive(3 - wg, 256);
      STAMP(21);
#pragma unroll
      for (int i = LD2; i < 8; i++) v[i] = ld_b128(xi + i * 1024);
      if (LD2 < 8) mbar_wait(bar_xres, 0);
      wg_wait<0>();
      keep(s);
      mbar_arrive_pred(bar_ring + 16, lane0);
      PROF(10, ct == PT, 23); STAMP(4);
#pragma unroll
      for (int i = 0; i < 16; i += 2) ldmatrix4((trow ^ ((i & 7) << 4)) + (i >> 3) * 16384, xr[2 * i], xr[2 * i + 1], xr[2 * i + 2], xr[2 * i + 3]);
      uint32_t ga[16];
      uint4 bw[8];
#pragma unroll
      for (int i = 0; i < 8; i++) {
        if (!(i & 1)) {
          const uint4 t = lds4(par + PAR_SINK + i * 32 + tq * 16);
          ga[2 * i] = t.x; ga[2 * i + 1] = t.y; ga[2 * i + 2] = t.z; ga[2 * i + 3] = t.w;
        }
        bw[i] = lds4(par + PAR_T1 + i * 64 + tq * 16);
        if (!(g & 1)) { bw[i].x = 0x3f803f80u; bw[i].y = 0x3f803f80u; }
      }
      uint32_t pk[32];
      pack_p(s, pk);
      keep(pk);
      {
        uint32_t n = 0, miss;
        do {
          miss = 0;
#pragma unroll
          for (int i = 0; i < 8; i++) miss |= v[i].x ^ par1;
          miss = __any_sync(0xffffffffu, miss & 0x10000u);
          if (miss) {
#pragma unroll
            for (int i = 0; i < 8; i++)
              asm volatile("{ .reg .pred p; .reg .b32 t; xor.b32 t, %0, %5; and.b32 t, t, 0x10000; setp.ne.u32 p, t, 0;\n"
                           "@p ld.relaxed.gpu.global.v4.u32 {%0, %1, %2, %3}, [%4]; }"
                           : "+r"(v[i].x), "+r"(v[i].y), "+r"(v[i].z), "+r"(v[i].w) : "l"(xi + i * 1024), "r"(par1) : "memory");
          }
          watchdog(n);
        } while (miss);
      }
      PROF(8, ct == PT, 22); STAMP(3);
      float ds[4] = {0.f, 0.f, 0.f, 0.f}, dl[4] = {0.f, 0.f, 0.f, 0.f}, q0[4] = {0.f, 0.f, 0.f, 0.f}, q1[4] = {0.f, 0.f, 0.f, 0.f};
#pragma unroll
      for (int i = 0; i < 8; i++) {
        const uint32_t u0 = hfma2(ga[2 * i], hadd2(pk[4 * i], v[i].x & ~0x10000u), xr[4 * i]);
        const uint32_t u1 = hfma2(ga[2 * i], hadd2(pk[4 * i + 1], v[i].y), xr[4 * i + 1]);
        const uint32_t u2 = hfma2(ga[2 * i + 1], hadd2(pk[4 * i + 2], v[i].z), xr[4 * i + 2]);
        const uint32_t u3 = hfma2(ga[2 * i + 1], hadd2(pk[4 * i + 3], v[i].w), xr[4 * i + 3]);
        xr[4 * i] = u0; xr[4 * i + 1] = u1; xr[4 * i + 2] = u2; xr[4 * i + 3] = u3;
        mma16816(ds, u0, u1, u2, u3, bw[i].x, bw[i].y);
        mma16816(dl, u0, u1, u2, u3, bw[i].z, bw[i].w);
        mma16816(q0, u0, u1, u2, u3, u0, u2);
        mma16816(q1, u0, u1, u2, u3, u1, u3);
      }
      const float sqa = __shfl_sync(0xffffffffu, (g & 1) ? q0[1] : q0[0], g * 4 + (g >> 1));
      const float sqb = __shfl_sync(0xffffffffu, (g & 1) ? q1[3] : q1[2], g * 4 + (g >> 1));
      own = (tq & 1) ? make_uint4(__float_as_uint(ds[2]), __float_as_uint(sqb), __float_as_uint(ds[3] + dl[3]), tag)
                                 : make_uint4(__float_as_uint(ds[0]), __float_as_uint(sqa), __float_as_uint(ds[1] + dl[1]), tag);
      if (tq < 2) st_b128(sp[0], own.x, own.y, own.z, own.w);
#pragma unroll
      for (int k = 0; k < 4; k++) sv[k] = make_uint4(0, 0, 0, 0);
    }
    PROF(8, ct == PT, 29); STAMP(5);
    uint32_t mm, ih, il;
    float rbest;
    uint32_t wf[128];
    const uint32_t frow = (ln & 7) + (ln >> 4) * 8;
    const uint32_t wfo = base + (warp & 1) * 8192 + frow * 64 + ((((ln >> 3) & 1) ^ ((frow >> 1) & 3)) << 4);
#define LOAD_WF(m) _Pragma("unroll") for (int f = 0; f < 16; f++) {                                                   \
      const int r = ((f >> 1) * 4 + (m) * 2 + (f & 1)) * 4;                                                           \
      ldmatrix4t(((wfo + unit_of((m) ? FT_U : FT_G, warp >> 1)) ^ ((f & 1) * 32)) + (f >> 1) * 1024, wf[r], wf[r + 1], wf[r + 2], wf[r + 3]); \
    }
    bool early;
    {
#pragma unroll
      for (int i = 0; i < 16; i += 2) stmatrix4((trow ^ ((i & 7) << 4)) + (i >> 3) * 16384, xr[2 * i], xr[2 * i + 1], xr[2 * i + 2], xr[2 * i + 3]);
      const uint4 cst = lds4(par + PAR_CONST);
      const float A1 = __uint_as_float(cst.x), A2 = __uint_as_float(cst.z);
      uint32_t n = 0;
      early = false;
#pragma unroll 1
      while (true) {
        uint32_t miss;
        asm volatile("{ .reg .pred p0, p1, p2, p3; .reg .b64 u, v; .reg .b128 w;\n"
                     "setp.ge.u32 p0, %22, 2; setp.ne.and.u32 p0, %4, %21, p0; setp.ne.u32 p1, %8, %21; setp.ne.u32 p2, %12, %21; setp.ne.u32 p3, %16, %21;\n"
                     "@p0 ld.relaxed.gpu.global.v4.u32 {%1, %2, %3, %4}, [%17];\n"
                     "@p1 ld.relaxed.gpu.global.v4.u32 {%5, %6, %7, %8}, [%18];\n"
                     "@p2 ld.relaxed.gpu.global.v4.u32 {%9, %10, %11, %12}, [%19];\n"
                     "@p3 ld.relaxed.gpu.global.v4.u32 {%13, %14, %15, %16}, [%20];\n"
                     "or.pred p0, p0, p1; or.pred p2, p2, p3; or.pred p0, p0, p2; vote.sync.any.pred p0, p0, 0xffffffff; selp.u32 %0, 1, 0, p0; }"
                     : "=r"(miss), "+r"(sv[0].x), "+r"(sv[0].y), "+r"(sv[0].z), "+r"(sv[0].w), "+r"(sv[1].x), "+r"(sv[1].y), "+r"(sv[1].z), "+r"(sv[1].w),
                       "+r"(sv[2].x), "+r"(sv[2].y), "+r"(sv[2].z), "+r"(sv[2].w), "+r"(sv[3].x), "+r"(sv[3].y), "+r"(sv[3].z), "+r"(sv[3].w)
                     : "l"(sp[0]), "l"(sp[1]), "l"(sp[2]), "l"(sp[3]), "r"(tag), "r"(tq) : "memory");
        if (!miss) break;
        if (!early && (b >= NFFN || __all_sync(0xffffffffu, mbar_test(bar_box + (warp >> 1) * 8, 0)))) {
          early = true;
          LOAD_WF(0);
          __syncwarp();
          mbar_arrive_pred(bar_gate, lane0);
        }
        watchdog(n);
      }
      const uint4 v0 = tq < 2 ? own : sv[0], v1 = sv[1], v2 = sv[2], v3 = sv[3];
      PROF(8, ct == PT, 30); STAMP(6);
      float su = (__uint_as_float(v0.x) + __uint_as_float(v1.x)) + (__uint_as_float(v2.x) + __uint_as_float(v3.x));
      float sq = (__uint_as_float(v0.y) + __uint_as_float(v1.y)) + (__uint_as_float(v2.y) + __uint_as_float(v3.y));
      float dt = (__uint_as_float(v0.z) + __uint_as_float(v1.z)) + (__uint_as_float(v2.z) + __uint_as_float(v3.z));
      su += __shfl_xor_sync(0xffffffffu, su, 2); sq += __shfl_xor_sync(0xffffffffu, sq, 2); dt += __shfl_xor_sync(0xffffffffu, dt, 2);
      const float m = su * (1.f / DM);
      float mb, sd;
      ln_scalars(m, fmaxf(sq * (1.f / DM) - m * m, 0.f), mb, sd);
      const float inv = rcp(sd);
      rbest = (dt - mb * A1) * inv + A2;
      mm = pack_bf(mb, mb);
      ih = pack_bf(inv, inv);
      const float lo = inv - bf_lo(ih);
      il = pack_bf(lo, lo);
    }
    int ibest;
    {
      const uint32_t bits = __float_as_uint(rbest);
      const uint32_t key = (((int)bits < 0 ? ~bits : bits | 0x80000000u) & ~0x1ffu) | ((127 - lrow0 - (tq & 1) * 8) << 2) | tag;
      sts1(par + PAR_RED + warp * 4, __reduce_max_sync(0xffffffffu, key));
      PROF(8, ct == PT, 38); STAMP(7);
      bar_sync(1, 256);
      const uint4 ka = lds4(par + PAR_RED), kb = lds4(par + PAR_RED + 16);
      const uint32_t k2 = max(max(max(ka.x, ka.y), max(ka.z, ka.w)), max(max(kb.x, kb.y), max(kb.z, kb.w)));
      if (ct == 0 && cj == 0) st_relaxed(g_cand + rb, k2);
      ibest = 127 - ((k2 >> 2) & 127);
    }
    PROF(8, ct == PT, 39); STAMP(8);
    if ((ibest >> 4) == warp) {
      const int src = (ibest & 7) * 4 + ((ibest >> 3) & 1), ch = g * 2;
      const uint32_t cm = __shfl_sync(0xffffffffu, mm, src), ch_ = __shfl_sync(0xffffffffu, ih, src), cl = __shfl_sync(0xffffffffu, il, src);
      const uint32_t xa = res + (ch >> 3) * 16384 + ibest * 128 + (((ch & 7) ^ (ibest & 7)) << 4) + tq * 4;
      const uint32_t x0 = lds1(xa), x1 = lds1(xa ^ 16);
      const uint2 p0 = lds2(par + PAR_T2 + ch * 64 + tq * 16), p1 = lds2(par + PAR_T2 + ch * 64 + 64 + tq * 16);
      uint32_t* dst = g_row + rb * 2 * DM + cj * 128 + ln * 4;
      st_pairs(dst, ln_mod(x0, cm, ch_, cl, p0.x, p0.y), ln_mod(x1, cm, ch_, cl, p1.x, p1.y), tag);
      st_pairs(dst + DM, x0, x1, tag);
      __syncwarp();
    }
    PROF(8, ct == PT, 37); STAMP(9);
    uint32_t wd[64];
    const uint32_t wda = base + unit_of(FT_D, warp >> 1) + (warp & 1) * 8192 + frow * 128 + ((((ln >> 3) & 1) ^ (ln & 7)) << 4);
#define LOAD_WD(f) ldmatrix4t((wda ^ ((((f) >> 1) & 3) * 32)) + ((f) >> 3) * 4096 + ((f) & 1) * 2048, wd[4 * (f)], wd[4 * (f) + 1], wd[4 * (f) + 2], wd[4 * (f) + 3])
    if (!early) {
      if (b < NFFN) mbar_wait(bar_box + (warp >> 1) * 8, 0);
      LOAD_WF(0);
      __syncwarp();
      mbar_arrive_pred(bar_gate, lane0);
    }
    if (b < NFFN) {
      const uint32_t own = base + unit_of(FT_G, warp >> 1) + (warp & 1) * 8192;
      mbar_wait(bar_box + (4 + (warp >> 1)) * 8, 0);
      LOAD_WF(1);
      uint32_t* const ydst = g_ypart + ((size_t)(warp * 16 + tq * 2) * NFFN + b) * 8 + g;
      PROF(8, ct == PT, 31); STAMP(10);
      bool wdok;
      {
        uint32_t n = 0;
        while (!(wdok = __all_sync(0xffffffffu, mbar_test(bar_box + (8 + (warp >> 1)) * 8, 0))) && !__all_sync(0xffffffffu, mbar_test(bar_sel, 0))) watchdog(n);
      }
      if (wdok) {
#pragma unroll
        for (int f = 0; f < 16; f++) LOAD_WD(f);
      }
      STAMP(11);
      mbar_wait(bar_sel, 0);
      PROF(8, ct == PT, 33); STAMP(12);
      float d[8][4];
#pragma unroll
      for (int i = 0; i < 4; i++) { d[i][0] = 0.f; d[i][1] = 0.f; d[i][2] = 0.f; d[i][3] = 0.f; }
#pragma unroll
      for (int ks = 0; ks < 8; ks++) {
        const uint2 hb = lds2(own + 256 + ks * 32 + tq * 8);
#pragma unroll
        for (int mt = 0; mt < 4; mt++) {
          const int r = ks * 16 + mt * 4;
          mma16816(d[mt], wf[r], wf[r + 1], wf[r + 2], wf[r + 3], hb.x, hb.y);
        }
      }
      sts2(own + (tq * 8 + g) * 8, __float_as_uint((tq & 2) ? ((tq & 1) ? d[1][2] : d[1][0]) : ((tq & 1) ? d[0][2] : d[0][0])),
           __float_as_uint((tq & 2) ? ((tq & 1) ? d[3][2] : d[3][0]) : ((tq & 1) ? d[2][2] : d[2][0])));
      bar_sync(1, 256);
      uint32_t ab[4];
      {
        float G = 0.f, U = 0.f;
        uint2 pv[8];
#pragma unroll
        for (int w8 = 0; w8 < 8; w8++) pv[w8] = lds2(base + ln * 8 + ((FT_G >> (w8 >> 1) * 4) & 15) * UNIT + (w8 & 1) * 8192);
#pragma unroll
        for (int w8 = 0; w8 < 8; w8 += 2) {
          G += __uint_as_float(pv[w8].x) + __uint_as_float(pv[w8 + 1].x);
          U += __uint_as_float(pv[w8].y) + __uint_as_float(pv[w8 + 1].y);
        }
        const float act = rbf(silu_f(rbf(G))) * rbf(U);
        const uint32_t pk = pack_bf(act, __shfl_down_sync(0xffffffffu, act, 1));
#pragma unroll
        for (int i = 0; i < 4; i++) ab[i] = __shfl_sync(0xffffffffu, pk, i * 8 + tq * 2);
      }
      if (!wdok) {
        mbar_wait(bar_box + (8 + (warp >> 1)) * 8, 0);
#pragma unroll
        for (int f = 0; f < 16; f++) LOAD_WD(f);
      }
      PROF(8, ct == PT, 34); STAMP(13);
#pragma unroll
      for (int mt = 0; mt < 8; mt++) {
        d[mt][0] = 0.f; d[mt][1] = 0.f; d[mt][2] = 0.f; d[mt][3] = 0.f;
        mma16816(d[mt], wd[mt * 8], wd[mt * 8 + 1], wd[mt * 8 + 2], wd[mt * 8 + 3], ab[0], ab[1]);
        mma16816(d[mt], wd[mt * 8 + 4], wd[mt * 8 + 5], wd[mt * 8 + 6], wd[mt * 8 + 7], ab[2], ab[3]);
      }
#pragma unroll
      for (int i = 0; i < 4; i++) {
        const int m4 = (i >> 1) * 4, e = (i & 1) * 2;
        const float y = (tq & 2) ? ((tq & 1) ? d[m4 + 3][e] : d[m4 + 2][e]) : ((tq & 1) ? d[m4 + 1][e] : d[m4][e]);
        st_relaxed(ydst + (m4 * 2 + (i & 1)) * NFFN * 8, tagf(y, tag));
      }
      PROF(8, ct == PT, 35); STAMP(14);
    }
    mbar_wait(bar_sel, 0);
    mbar_arrive_pred(bar_win, ct == 0);
    const int iwin = lds1(par + PAR_CONST + 60) & 0x7ff;
    const bool cand = (iwin >> 4) == rb * 8 + warp;
    {
      const uint32_t mm0 = __shfl_sync(0xffffffffu, mm, ln & ~1), mm1 = __shfl_sync(0xffffffffu, mm, ln | 1);
      const uint32_t ih0 = __shfl_sync(0xffffffffu, ih, ln & ~1), ih1 = __shfl_sync(0xffffffffu, ih, ln | 1);
      const uint32_t il0 = __shfl_sync(0xffffffffu, il, ln & ~1), il1 = __shfl_sync(0xffffffffu, il, ln | 1);
#pragma unroll 1
      for (int hf = 0; hf < 2; hf++) {
        uint32_t x[16];
#pragma unroll
        for (int i = 0; i < 8; i += 2) ldmatrix4((trow ^ (i << 4)) + hf * 16384, x[2 * i], x[2 * i + 1], x[2 * i + 2], x[2 * i + 3]);
#pragma unroll
        for (int i = 0; i < 8; i++) {
          const uint4 pv = lds4(par + PAR_T2 + (hf * 8 + i) * 64 + tq * 16);
          x[2 * i] = hadd2(x[2 * i], hmul2(pv.z, ln_mod(x[2 * i], mm0, ih0, il0, pv.x, pv.y)));
          x[2 * i + 1] = hadd2(x[2 * i + 1], hmul2(pv.z, ln_mod(x[2 * i + 1], mm1, ih1, il1, pv.x, pv.y)));
        }
#pragma unroll
        for (int i = 0; i < 8; i += 2) stmatrix4((trow ^ (i << 4)) + hf * 16384, x[2 * i], x[2 * i + 1], x[2 * i + 2], x[2 * i + 3]);
      }
      if (!cand) fence_async_smem();
      __syncwarp();
      if (!cand && elect_one()) {
        tma2d_store(&maps.out, res + warp * 2048, cj * 128, rb * 128 + warp * 16);
        tma2d_store(&maps.out, res + 16384 + warp * 2048, cj * 128 + 64, rb * 128 + warp * 16);
        asm volatile("cp.async.bulk.commit_group;" ::: "memory");
      }
    }
    if (cand) {
      const int wrow0 = warp * 16;
#pragma unroll 2
      for (int p = 0; p < 8; p++) {
        const int row = 2 * p + (ln >> 4), ch = ln & 15;
        const uint4 v = lds4(res + (ch >> 3) * 16384 + (wrow0 + row) * 128 + (((ch & 7) ^ (row & 7)) << 4));
        if (rb * 128 + wrow0 + row != iwin) *reinterpret_cast<uint4*>(P.out + (size_t)(rb * 128 + wrow0 + row) * DM + cj * 128 + ch * 8) = v;
      }
    }
    asm volatile("cp.async.bulk.wait_group.read 0;" ::: "memory");
    PROF(8, ct == PT, 11); STAMP(15);
    cluster_wait();
  }
}

typedef CUresult (*EncodeFn)(CUtensorMap*, CUtensorMapDataType, cuuint32_t, void*, const cuuint64_t*, const cuuint64_t*,
                             const cuuint32_t*, const cuuint32_t*, CUtensorMapInterleave, CUtensorMapSwizzle,
                             CUtensorMapL2promotion, CUtensorMapFloatOOBfill);

void map2d(EncodeFn enc, CUtensorMap* m, const void* p, uint64_t rows, uint64_t cols, uint32_t brows) {
  cuuint64_t dims[2] = {cols, rows}, strides[1] = {cols * 2};
  cuuint32_t box[2] = {64, brows}, es[2] = {1, 1};
  enc(m, CU_TENSOR_MAP_DATA_TYPE_BFLOAT16, 2, const_cast<void*>(p), dims, strides, box, es, CU_TENSOR_MAP_INTERLEAVE_NONE,
      CU_TENSOR_MAP_SWIZZLE_128B, CU_TENSOR_MAP_L2_PROMOTION_L2_256B, CU_TENSOR_MAP_FLOAT_OOB_FILL_NONE);
}
void map2d_narrow(EncodeFn enc, CUtensorMap* m, const void* p, uint64_t rows, uint64_t cols, uint32_t brows) {
  cuuint64_t dims[2] = {cols, rows}, strides[1] = {cols * 2};
  cuuint32_t box[2] = {32, brows}, es[2] = {1, 1};
  enc(m, CU_TENSOR_MAP_DATA_TYPE_BFLOAT16, 2, const_cast<void*>(p), dims, strides, box, es, CU_TENSOR_MAP_INTERLEAVE_NONE,
      CU_TENSOR_MAP_SWIZZLE_64B, CU_TENSOR_MAP_L2_PROMOTION_L2_64B, CU_TENSOR_MAP_FLOAT_OOB_FILL_NONE);
}
void map3d(EncodeFn enc, CUtensorMap* m, const void* p, uint64_t rows, uint64_t cols, uint32_t brows, uint32_t nch) {
  cuuint64_t dims[3] = {64, rows, cols / 64}, strides[2] = {cols * 2, 128};
  cuuint32_t box[3] = {64, brows, nch}, es[3] = {1, 1, 1};
  enc(m, CU_TENSOR_MAP_DATA_TYPE_BFLOAT16, 3, const_cast<void*>(p), dims, strides, box, es, CU_TENSOR_MAP_INTERLEAVE_NONE,
      CU_TENSOR_MAP_SWIZZLE_128B, CU_TENSOR_MAP_L2_PROMOTION_L2_256B, CU_TENSOR_MAP_FLOAT_OOB_FILL_NONE);
}

}

extern "C" void kernel_launch(void* const* d_in, const int* in_sizes, int n_in, void* d_out, int out_size) {
  (void)in_sizes; (void)n_in; (void)out_size;
  static EncodeFn enc = nullptr;
  if (!enc) {
    void* fn = nullptr;
    cudaDriverEntryPointQueryResult st;
    cudaGetDriverEntryPoint("cuTensorMapEncodeTiled", &fn, cudaEnableDefault, &st);
    enc = (EncodeFn)fn;
    cudaFuncSetAttribute(fused_kernel, cudaFuncAttributeMaxDynamicSharedMemorySize, SMEM_BYTES);
  }
  Maps maps;
  map2d(enc, &maps.x, d_in[0], SEQ, DM, 128);
  map2d(enc, &maps.out, d_out, SEQ, DM, 16);
  map3d(enc, &maps.wq, d_in[3], DM, NQ, 64, 2);
  map3d(enc, &maps.k, d_in[1], 4 * SK, 128, 128, 1);
  map3d(enc, &maps.v, d_in[2], 4 * SK, 128, 128, 1);
  map3d(enc, &maps.wo, d_in[4], NQ, DM, 64, 2);
  map2d_narrow(enc, &maps.wg, d_in[7], DM, FF, 256);
  map2d_narrow(enc, &maps.wu, d_in[8], DM, FF, 256);
  map3d(enc, &maps.wd, d_in[9], FF, DM, 32, 4);
  map2d_narrow(enc, &maps.wm, d_in[11], DM, NMOD, 256);
  Ptrs p;
  p.x = (const __nv_bfloat16*)d_in[0];
  p.w_r = (const __nv_bfloat16*)d_in[6];
  p.w_gate = (const __nv_bfloat16*)d_in[7];
  p.w_up = (const __nv_bfloat16*)d_in[8];
  p.w_down = (const __nv_bfloat16*)d_in[9];
  p.c = (const __nv_bfloat16*)d_in[10];
  p.w_mod = (const __nv_bfloat16*)d_in[11];
  p.out = (__nv_bfloat16*)d_out;
  fused_kernel<<<NMAIN + NHELP, 384, SMEM_BYTES>>>(maps, p);
}
```

```cpp
#include <cuda_runtime.h>
#include <cuda_bf16.h>
#include <cuda.h>
#include <stdint.h>
#include <type_traits>

#define HD 2
#define HDX 2
#define NRS 8
#define FPACE 3
#define GOST 20
#define WB 2
#define WN 20
#define RES0 17
#define RES1 20
#define HU 32
#define NS1 5
#define PG0 15
#define FB0 0
#define FB2 8
#define OPS 8192
#define OFL 0
#define ODS 8
#define MODUL hfma2
#define ODS1 5
#define LD1 0
#define LD2 4
#define FB1 2
#define FPB 8
#define FPACE0 2
#define OSL 900
#define OSL2 400
#define CR 8
#define CS 8
#define YPULL 0
#define VREL 5
#define E0 3

namespace {

constexpr int SEQ = 2048, DM = 1024, NQ = 4096, SK = 2048, WIN = 512, FF = 3584, NMOD = 6144;
constexpr int NMAIN = 128, NHELP = 4, NFFN = 112;
constexpr int NSLOT = 4, SLOT_BYTES = 32768, UNIT = 16384, GST_BYTES = 3 * UNIT;
constexpr uint32_t XT1 = 0xDCBA, XT2 = 0x9687;
constexpr uint32_t WT0 = 0xA741, WT1 = 0x7420, WT2 = 0x4A20;
constexpr uint32_t AT0 = WT1, AT1 = WT2;
constexpr uint32_t QT = 0xDC9696DC;
constexpr int OFF_STAGE = 12 * UNIT;
constexpr uint32_t FT_G = 0x07B3, FT_U = 0xA628, FT_D = 0x5149;
constexpr int OFF_RES = 12 * UNIT;
constexpr int OFF_PAR = 14 * UNIT;
constexpr int OFF_BAR = OFF_PAR + 2528;
constexpr int SMEM_BYTES = OFF_BAR + 544;
static_assert(SMEM_BYTES <= 232448, "smem");

constexpr int PAR_T1 = 0;
constexpr int PAR_T2 = 512;
constexpr int PAR_CONST = 1536;
constexpr int PAR_RED = 1600;
constexpr int PAR_SINK = 2176;

struct Maps {
  CUtensorMap x, wq, k, v, wo, wg, wu, wd, wm, out;
};
struct Ptrs {
  const __nv_bfloat16 *x, *w_r, *c, *w_mod, *w_gate, *w_up, *w_down;
  __nv_bfloat16* out;
};

__device__ __align__(1024) uint8_t g_act[16 * 80 * UNIT];
__device__ __align__(128) uint32_t g_mod[NMOD];
__device__ __align__(128) uint32_t g_modp[2 * 2 * DM];
__device__ __align__(128) uint32_t g_ln1[SEQ * 4];
__device__ __align__(128) uint32_t g_cnt_h[16 * 32];
__device__ __align__(128) uint32_t g_cnt_o[128 * 32];
__device__ __align__(128) uint32_t g_xch[NMAIN * 8 * 256 * 4];
__device__ __align__(128) uint32_t g_stats[8 * SEQ * 4];
__device__ __align__(128) uint32_t g_cand[CR * 512];
__device__ __align__(128) uint32_t g_row[16 * 2 * DM];
__device__ __align__(128) uint32_t g_ypart[NMAIN * NFFN * 4];
__device__ __forceinline__ uint32_t* ypart_slot(int writer, int reader) { return g_ypart + (YPULL ? writer * NMAIN + reader : reader * NFFN + writer) * 4; }
__device__ uint32_t g_epoch;

__device__ __forceinline__ uint32_t fresh_lane() { uint32_t l; asm volatile("mov.u32 %0, %%laneid;" : "=r"(l)); return l; }
__device__ __forceinline__ uint32_t frag_offset(int warp) {
  const uint32_t l = fresh_lane();
  return ((warp & 3) * 16 + (l & 15)) * 128 + (((l >> 4) ^ (l & 7)) << 4);
}
__device__ __forceinline__ bool elect_one() {
  uint32_t p;
  asm volatile("{ .reg .pred q; elect.sync _|q, 0xffffffff; selp.u32 %0, 1, 0, q; }" : "=r"(p));
  return p;
}
__device__ __forceinline__ uint32_t smem_u32(const void* p) { return (uint32_t)__cvta_generic_to_shared(p); }
__device__ __forceinline__ void mbar_init(uint32_t bar, uint32_t cnt) {
  asm volatile("mbarrier.init.shared::cta.b64 [%0], %1;" ::"r"(bar), "r"(cnt) : "memory");
}
__device__ __forceinline__ void mbar_expect_tx(uint32_t bar, uint32_t bytes) {
  asm volatile("mbarrier.arrive.expect_tx.shared::cta.b64 _, [%0], %1;" ::"r"(bar), "r"(bytes) : "memory");
}
__device__ __forceinline__ void mbar_arrive(uint32_t bar) {
  asm volatile("mbarrier.arrive.shared::cta.b64 _, [%0];" ::"r"(bar) : "memory");
}
__device__ __forceinline__ void mbar_arrive_pred(uint32_t bar, bool p) {
  asm volatile("{ .reg .pred p; setp.ne.b32 p, %1, 0; @p mbarrier.arrive.shared::cta.b64 _, [%0]; }" ::"r"(bar), "r"((int)p) : "memory");
}
__device__ __forceinline__ void mbar_arrive_cl(uint32_t bar, uint32_t off, bool p = true) {
  asm volatile("{ .reg .pred p, q; .reg .b32 a; setp.ne.b32 q, %2, 0; setp.ne.and.b32 p, %0, 0, q; add.u32 a, %0, %1; @p mbarrier.arrive.shared::cluster.b64 _, [a]; }"
               ::"r"(bar), "r"(off), "r"((int)p) : "memory");
}
__device__ __forceinline__ uint32_t mapa(uint32_t addr, uint32_t cta) {
  uint32_t r; asm("mapa.shared::cluster.u32 %0, %1, %2;" : "=r"(r) : "r"(addr), "r"(cta)); return r;
}
__device__ __forceinline__ void cluster_arrive() { asm volatile("barrier.cluster.arrive.relaxed.aligned;" ::: "memory"); }
__device__ __forceinline__ void cluster_wait() { asm volatile("barrier.cluster.wait.aligned;" ::: "memory"); }
__device__ __forceinline__ void watchdog(uint32_t& n) {
}
__device__ __forceinline__ void mbar_wait(uint32_t bar, uint32_t parity) {
  asm volatile("{\n.reg .pred p;\nWAIT_%=:\nmbarrier.try_wait.parity.shared::cta.b64 p, [%0], %1;\n@!p bra WAIT_%=;\n}" ::"r"(bar), "r"(parity) : "memory");
}
__device__ __forceinline__ bool mbar_test(uint32_t bar, uint32_t parity) {
  uint32_t ok;
  asm volatile("{\n.reg .pred p;\nmbarrier.test_wait.parity.shared::cta.b64 p, [%1], %2;\nselp.u32 %0, 1, 0, p;\n}" : "=r"(ok) : "r"(bar), "r"(parity) : "memory");
  return ok;
}
__device__ __forceinline__ uint64_t l2_stream() {
  uint64_t f; asm("createpolicy.fractional.L2::evict_first.b64 %0, 1.0;" : "=l"(f)); return f;
}
__device__ __forceinline__ void tma2d(uint32_t dst, const CUtensorMap* m, int c0, int c1, uint32_t bar) {
  asm volatile("cp.async.bulk.tensor.2d.shared::cluster.global.mbarrier::complete_tx::bytes.L2::cache_hint [%0], [%1, {%3, %4}], [%2], %5;"
               ::"r"(dst), "l"(m), "r"(bar), "r"(c0), "r"(c1), "l"(l2_stream()) : "memory");
}
__device__ __forceinline__ void bulk_load(uint32_t dst, const void* src, uint32_t bytes, uint32_t bar) {
  asm volatile("cp.async.bulk.shared::cluster.global.mbarrier::complete_tx::bytes [%0], [%1], %2, [%3];" ::"r"(dst), "l"(src), "r"(bytes), "r"(bar) : "memory");
}
__device__ __forceinline__ void bulk_load_stream(uint32_t dst, const void* src, uint32_t bytes, uint32_t bar) {
  asm volatile("cp.async.bulk.shared::cluster.global.mbarrier::complete_tx::bytes.L2::cache_hint [%0], [%1], %2, [%3], %4;"
               ::"r"(dst), "l"(src), "r"(bytes), "r"(bar), "l"(l2_stream()) : "memory");
}
__device__ __forceinline__ void tma2d_store(const CUtensorMap* m, uint32_t src, int c0, int c1) {
  asm volatile("cp.async.bulk.tensor.2d.global.shared::cta.bulk_group [%0, {%2, %3}], [%1];" ::"l"(m), "r"(src), "r"(c0), "r"(c1) : "memory");
}
__device__ __forceinline__ void bulk_store(void* dst, uint32_t src, uint32_t bytes) {
  asm volatile("cp.async.bulk.global.shared::cta.bulk_group [%0], [%1], %2;" ::"l"(dst), "r"(src), "r"(bytes) : "memory");
}
__device__ __forceinline__ int slice_of(int i) { return i + ((i & 7) == 1) - ((i & 7) == 2); }
__device__ __forceinline__ uint32_t unit_of(uint32_t table, uint32_t i) { return ((table >> (i * 4)) & 15) * UNIT; }
__device__ __forceinline__ void tma3d(uint32_t dst, const CUtensorMap* m, int c0, int c1, int c2, uint32_t bar) {
  asm volatile("cp.async.bulk.tensor.3d.shared::cluster.global.mbarrier::complete_tx::bytes.L2::cache_hint [%0], [%1, {%3, %4, %5}], [%2], %6;"
               ::"r"(dst), "l"(m), "r"(bar), "r"(c0), "r"(c1), "r"(c2), "l"(l2_stream()) : "memory");
}
template <bool STREAM>
__device__ __forceinline__ void tma3d_mc(uint32_t dst, const CUtensorMap* m, int c0, int c1, int c2, uint32_t bar) {
  if (STREAM)
    asm volatile("cp.async.bulk.tensor.3d.shared::cluster.global.mbarrier::complete_tx::bytes.multicast::cluster.L2::cache_hint [%0], [%1, {%3, %4, %5}], [%2], %6, %7;"
                 ::"r"(dst), "l"(m), "r"(bar), "r"(c0), "r"(c1), "r"(c2), "h"((uint16_t)3), "l"(l2_stream()) : "memory");
  else
    asm volatile("cp.async.bulk.tensor.3d.shared::cluster.global.mbarrier::complete_tx::bytes.multicast::cluster [%0], [%1, {%3, %4, %5}], [%2], %6;"
                 ::"r"(dst), "l"(m), "r"(bar), "r"(c0), "r"(c1), "r"(c2), "h"((uint16_t)3) : "memory");
}
__device__ __forceinline__ void prefetch_map(const CUtensorMap* m) {
  asm volatile("prefetch.tensormap [%0];" ::"l"(m) : "memory");
}
__device__ __forceinline__ void fence_async() { asm volatile("fence.proxy.async.global;" ::: "memory"); }
__device__ __forceinline__ void fence_async_smem() { asm volatile("fence.proxy.async.shared::cta;" ::: "memory"); }
__device__ __forceinline__ void bar_sync(int id, int n) { asm volatile("bar.sync %0, %1;" ::"r"(id), "r"(n) : "memory"); }
__device__ __forceinline__ void bar_arrive(int id, int n) { asm volatile("bar.arrive %0, %1;" ::"r"(id), "r"(n) : "memory"); }
__device__ __forceinline__ void wg_fence() { asm volatile("wgmma.fence.sync.aligned;" ::: "memory"); }
__device__ __forceinline__ void wg_commit() { asm volatile("wgmma.commit_group.sync.aligned;" ::: "memory"); }
template <int N> __device__ __forceinline__ void wg_wait() { asm volatile("wgmma.wait_group.sync.aligned %0;" ::"n"(N) : "memory"); }
__device__ __forceinline__ uint64_t make_desc(uint32_t addr, uint32_t lbo, uint32_t sbo) {
  return (uint64_t)((addr & 0x3FFFF) >> 4) | ((uint64_t)(lbo >> 4) << 16) | ((uint64_t)(sbo >> 4) << 32) | (1ull << 62);
}
__device__ __forceinline__ uint32_t ld_relaxed(const uint32_t* p) {
  uint32_t v; asm volatile("ld.relaxed.gpu.global.u32 %0, [%1];" : "=r"(v) : "l"(p) : "memory"); return v;
}
__device__ __forceinline__ uint32_t ld_acquire(const uint32_t* p) {
  uint32_t v; asm volatile("ld.acquire.gpu.global.u32 %0, [%1];" : "=r"(v) : "l"(p) : "memory"); return v;
}
__device__ __forceinline__ uint4 ld_relaxed4(const uint32_t* p) {
  uint4 v; asm volatile("ld.relaxed.gpu.global.v4.u32 {%0,%1,%2,%3}, [%4];" : "=r"(v.x), "=r"(v.y), "=r"(v.z), "=r"(v.w) : "l"(p) : "memory"); return v;
}
__device__ __forceinline__ uint2 ld_relaxed2(const uint32_t* p) {
  uint2 v; asm volatile("ld.relaxed.gpu.global.v2.u32 {%0,%1}, [%2];" : "=r"(v.x), "=r"(v.y) : "l"(p) : "memory"); return v;
}
__device__ __forceinline__ void st_relaxed(uint32_t* p, uint32_t v) {
  asm volatile("st.relaxed.gpu.global.u32 [%0], %1;" ::"l"(p), "r"(v) : "memory");
}
__device__ __forceinline__ void st_relaxed2(uint32_t* p, uint32_t a, uint32_t b) {
  asm volatile("st.relaxed.gpu.global.v2.u32 [%0], {%1,%2};" ::"l"(p), "r"(a), "r"(b) : "memory");
}
__device__ __forceinline__ void st_relaxed4(uint32_t* p, uint32_t a, uint32_t b, uint32_t c, uint32_t d) {
  asm volatile("st.relaxed.gpu.global.v4.u32 [%0], {%1,%2,%3,%4};" ::"l"(p), "r"(a), "r"(b), "r"(c), "r"(d) : "memory");
}
__device__ __forceinline__ void st_b128(uint32_t* p, uint32_t a, uint32_t b, uint32_t c, uint32_t d) {
  asm volatile("{ .reg .b64 u, v; .reg .b128 w; mov.b64 u, {%1, %2}; mov.b64 v, {%3, %4}; mov.b128 w, {u, v}; st.relaxed.gpu.global.b128 [%0], w; }"
               ::"l"(p), "r"(a), "r"(b), "r"(c), "r"(d) : "memory");
}
__device__ __forceinline__ uint4 ld_b128(const uint32_t* p) {
  uint4 r;
  asm volatile("{ .reg .b64 u, v; .reg .b128 w; ld.relaxed.gpu.global.b128 w, [%4]; mov.b128 {u, v}, w; mov.b64 {%0, %1}, u; mov.b64 {%2, %3}, v; }"
               : "=r"(r.x), "=r"(r.y), "=r"(r.z), "=r"(r.w) : "l"(p) : "memory");
  return r;
}
__device__ __forceinline__ void st_pairs(uint32_t* p, uint32_t a, uint32_t b, uint32_t tag) {
  asm volatile("{ .reg .b64 u, v; mov.b64 u, {%1, %3}; mov.b64 v, {%2, %3}; st.relaxed.gpu.global.v2.b64 [%0], {u, v}; }"
               ::"l"(p), "r"(a), "r"(b), "r"(tag) : "memory");
}
__device__ __forceinline__ uint4 ld_pairs(const uint32_t* p) {
  uint4 v;
  asm volatile("{ .reg .b64 u, v; ld.relaxed.gpu.global.v2.b64 {u, v}, [%4]; mov.b64 {%0, %1}, u; mov.b64 {%2, %3}, v; }"
               : "=r"(v.x), "=r"(v.y), "=r"(v.z), "=r"(v.w) : "l"(p) : "memory");
  return v;
}
__device__ __forceinline__ uint2 ld_pair(const uint32_t* p) {
  uint2 v;
  asm volatile("{ .reg .b64 u; ld.relaxed.gpu.global.b64 u, [%2]; mov.b64 {%0, %1}, u; }" : "=r"(v.x), "=r"(v.y) : "l"(p) : "memory");
  return v;
}
__device__ __forceinline__ void red_release(uint32_t* p, uint32_t v) {
  asm volatile("red.release.gpu.global.add.u32 [%0], %1;" ::"l"(p), "r"(v) : "memory");
}
__device__ __forceinline__ uint32_t ldg_nc1(const void* p) {
  uint32_t v;
  asm volatile("ld.global.nc.u32 %0, [%1];" : "=r"(v) : "l"(p));
  return v;
}
__device__ __forceinline__ uint4 ldg_nc4(const void* p) {
  uint4 v; asm volatile("ld.global.nc.L1::no_allocate.v4.u32 {%0,%1,%2,%3}, [%4];" : "=r"(v.x), "=r"(v.y), "=r"(v.z), "=r"(v.w) : "l"(p)); return v;
}
__device__ __forceinline__ uint4 ldg_stream4(const void* p) {
  uint4 v;
  asm volatile("ld.global.nc.L1::no_allocate.L2::cache_hint.v4.u32 {%0,%1,%2,%3}, [%4], %5;" : "=r"(v.x), "=r"(v.y), "=r"(v.z), "=r"(v.w) : "l"(p), "l"(l2_stream()));
  return v;
}
__device__ __forceinline__ void stg4(void* p, uint4 v) {
  asm volatile("st.global.v4.u32 [%0], {%1,%2,%3,%4};" ::"l"(p), "r"(v.x), "r"(v.y), "r"(v.z), "r"(v.w) : "memory");
}
__device__ __forceinline__ void wait_counter(const uint32_t* p, uint32_t target) {
  uint32_t n = 0;
  while (__any_sync(0xffffffffu, (int)(ld_acquire(p) - target) < 0)) { watchdog(n); }
}
__device__ __forceinline__ uint32_t tagf(float v, uint32_t tag) { return (__float_as_uint(v) & ~3u) | tag; }
__device__ __forceinline__ bool tag_ok(uint4 v, uint32_t tag) { return (((v.x ^ tag) | (v.y ^ tag) | (v.z ^ tag) | (v.w ^ tag)) & 3u) == 0; }
__device__ __forceinline__ float untag_sum(uint32_t a, uint32_t b) { return __uint_as_float(a & ~3u) + __uint_as_float(b & ~3u); }
__device__ __forceinline__ uint4 poll4(const uint32_t* p, uint32_t tag) {
  uint4 v = ld_relaxed4(p);
  uint32_t n = 0;
  while (!__all_sync(0xffffffffu, tag_ok(v, tag))) { v = ld_relaxed4(p); watchdog(n); }
  return v;
}
__device__ __forceinline__ float bf_lo(uint32_t v) { return __uint_as_float(v << 16); }
__device__ __forceinline__ float bf_hi(uint32_t v) { return __uint_as_float(v & 0xffff0000u); }
__device__ __forceinline__ uint32_t pack_bf(float lo, float hi) {
  uint32_t r; asm("cvt.rn.bf16x2.f32 %0, %1, %2;" : "=r"(r) : "f"(hi), "f"(lo)); return r;
}
__device__ __forceinline__ float rbf(float v) { return __uint_as_float(pack_bf(0.f, v) & 0xffff0000u); }
__device__ __forceinline__ uint32_t hmul2(uint32_t a, uint32_t b) {
  uint32_t r; asm("mul.rn.bf16x2 %0, %1, %2;" : "=r"(r) : "r"(a), "r"(b)); return r;
}
__device__ __forceinline__ uint32_t hadd2(uint32_t a, uint32_t b) {
  uint32_t r; asm("add.rn.bf16x2 %0, %1, %2;" : "=r"(r) : "r"(a), "r"(b)); return r;
}
__device__ __forceinline__ uint32_t hsub2(uint32_t a, uint32_t b) {
  uint32_t r; asm("sub.rn.bf16x2 %0, %1, %2;" : "=r"(r) : "r"(a), "r"(b)); return r;
}
__device__ __forceinline__ uint32_t hmax2(uint32_t a, uint32_t b) {
  uint32_t r; asm("max.bf16x2 %0, %1, %2;" : "=r"(r) : "r"(a), "r"(b)); return r;
}
__device__ __forceinline__ float rcp(float x) { float r; asm("rcp.approx.ftz.f32 %0, %1;" : "=f"(r) : "f"(x)); return r; }
__device__ __forceinline__ float ex2(float x) { float r; asm("ex2.approx.ftz.f32 %0, %1;" : "=f"(r) : "f"(x)); return r; }
__device__ __forceinline__ void stmatrix4(uint32_t addr, uint32_t a, uint32_t b, uint32_t c, uint32_t d) {
  asm volatile("stmatrix.sync.aligned.m8n8.x4.shared.b16 [%0], {%1,%2,%3,%4};" ::"r"(addr), "r"(a), "r"(b), "r"(c), "r"(d) : "memory");
}
__device__ __forceinline__ void ldmatrix4(uint32_t addr, uint32_t& a, uint32_t& b, uint32_t& c, uint32_t& d) {
  asm volatile("ldmatrix.sync.aligned.m8n8.x4.shared.b16 {%0,%1,%2,%3}, [%4];" : "=r"(a), "=r"(b), "=r"(c), "=r"(d) : "r"(addr) : "memory");
}
__device__ __forceinline__ void ldmatrix4t(uint32_t addr, uint32_t& a, uint32_t& b, uint32_t& c, uint32_t& d) {
  asm volatile("ldmatrix.sync.aligned.m8n8.x4.trans.shared.b16 {%0,%1,%2,%3}, [%4];" : "=r"(a), "=r"(b), "=r"(c), "=r"(d) : "r"(addr) : "memory");
}
__device__ __forceinline__ void mma16816(float (&d)[4], uint32_t a0, uint32_t a1, uint32_t a2, uint32_t a3, uint32_t b0, uint32_t b1) {
  asm volatile("mma.sync.aligned.m16n8k16.row.col.f32.bf16.bf16.f32 {%0,%1,%2,%3}, {%4,%5,%6,%7}, {%8,%9}, {%0,%1,%2,%3};"
               : "+f"(d[0]), "+f"(d[1]), "+f"(d[2]), "+f"(d[3]) : "r"(a0), "r"(a1), "r"(a2), "r"(a3), "r"(b0), "r"(b1));
}
__device__ __forceinline__ void sts1(uint32_t a, uint32_t v) { asm volatile("st.shared.u32 [%0], %1;" ::"r"(a), "r"(v) : "memory"); }
__device__ __forceinline__ uint4 lds4(uint32_t a) {
  uint4 v; asm volatile("ld.shared.v4.u32 {%0,%1,%2,%3}, [%4];" : "=r"(v.x), "=r"(v.y), "=r"(v.z), "=r"(v.w) : "r"(a) : "memory"); return v;
}
__device__ __forceinline__ uint2 lds2(uint32_t a) {
  uint2 v; asm volatile("ld.shared.v2.u32 {%0,%1}, [%2];" : "=r"(v.x), "=r"(v.y) : "r"(a) : "memory"); return v;
}
__device__ __forceinline__ uint32_t lds1(uint32_t a) {
  uint32_t v; asm volatile("ld.shared.u32 %0, [%1];" : "=r"(v) : "r"(a) : "memory"); return v;
}
__device__ __forceinline__ void sts2(uint32_t a, uint32_t x, uint32_t y) { asm volatile("st.shared.v2.u32 [%0], {%1,%2};" ::"r"(a), "r"(x), "r"(y) : "memory"); }
__device__ __forceinline__ void sts4(uint32_t a, uint4 v) {
  asm volatile("st.shared.v4.u32 [%0], {%1,%2,%3,%4};" ::"r"(a), "r"(v.x), "r"(v.y), "r"(v.z), "r"(v.w) : "memory");
}
__device__ __forceinline__ float silu_f(float v) { return __fdividef(v, 1.f + __expf(-v)); }
__device__ __forceinline__ uint32_t hfma2(uint32_t a, uint32_t b, uint32_t c) {
  uint32_t r; asm("fma.rn.bf16x2 %0, %1, %2, %3;" : "=r"(r) : "r"(a), "r"(b), "r"(c)); return r;
}
__device__ __forceinline__ void split_inv(float sd, uint32_t& ih, uint32_t& il) {
  const float inv = rcp(sd);
  ih = pack_bf(inv, inv);
  const float lo = inv - bf_lo(ih);
  il = pack_bf(lo, lo);
}
__device__ __forceinline__ uint32_t ln_norm(uint32_t x, uint32_t mean2, uint32_t ih, uint32_t il) {
  const uint32_t d = hsub2(x, mean2);
  return hfma2(d, ih, hmul2(d, il));
}
__device__ __forceinline__ uint32_t modul(uint32_t n, uint32_t c1, uint32_t sh) { return hadd2(hmul2(n, c1), sh); }
__device__ __forceinline__ uint32_t ln_mod(uint32_t x, uint32_t mean2, uint32_t ih, uint32_t il, uint32_t c1, uint32_t sh) {
  return modul(ln_norm(x, mean2, ih, il), c1, sh);
}

#define R8(a, i) "+f"(a[i]), "+f"(a[i + 1]), "+f"(a[i + 2]), "+f"(a[i + 3]), "+f"(a[i + 4]), "+f"(a[i + 5]), "+f"(a[i + 6]), "+f"(a[i + 7])
#define D64 "{%0,%1,%2,%3,%4,%5,%6,%7,%8,%9,%10,%11,%12,%13,%14,%15,%16,%17,%18,%19,%20,%21,%22,%23,%24,%25,%26,%27,%28,%29,%30,%31," \
            "%32,%33,%34,%35,%36,%37,%38,%39,%40,%41,%42,%43,%44,%45,%46,%47,%48,%49,%50,%51,%52,%53,%54,%55,%56,%57,%58,%59,%60,%61,%62,%63}"
template <int TB>
__device__ __forceinline__ void mma_ss(float (&d)[64], uint64_t da, uint64_t db, int sc) {
  asm volatile("{\n.reg .pred p;\nsetp.ne.b32 p, %66, 0;\n"
               "wgmma.mma_async.sync.aligned.m64n128k16.f32.bf16.bf16 " D64 ", %64, %65, p, 1, 1, 0, %67;\n}"
               : R8(d, 0), R8(d, 8), R8(d, 16), R8(d, 24), R8(d, 32), R8(d, 40), R8(d, 48), R8(d, 56)
               : "l"(da), "l"(db), "r"(sc), "n"(TB));
}
template <int TB>
__device__ __forceinline__ void mma_rs(float (&d)[64], uint32_t a0, uint32_t a1, uint32_t a2, uint32_t a3, uint64_t db, int sc) {
  asm volatile("{\n.reg .pred p;\nsetp.ne.b32 p, %69, 0;\n"
               "wgmma.mma_async.sync.aligned.m64n128k16.f32.bf16.bf16 " D64 ", {%64,%65,%66,%67}, %68, p, 1, 1, %70;\n}"
               : R8(d, 0), R8(d, 8), R8(d, 16), R8(d, 24), R8(d, 32), R8(d, 40), R8(d, 48), R8(d, 56)
               : "r"(a0), "r"(a1), "r"(a2), "r"(a3), "l"(db), "r"(sc), "n"(TB));
}
#define D128 "{%0,%1,%2,%3,%4,%5,%6,%7,%8,%9,%10,%11,%12,%13,%14,%15,%16,%17,%18,%19,%20,%21,%22,%23,%24,%25,%26,%27,%28,%29,%30,%31," \
             "%32,%33,%34,%35,%36,%37,%38,%39,%40,%41,%42,%43,%44,%45,%46,%47,%48,%49,%50,%51,%52,%53,%54,%55,%56,%57,%58,%59,%60,%61,%62,%63," \
             "%64,%65,%66,%67,%68,%69,%70,%71,%72,%73,%74,%75,%76,%77,%78,%79,%80,%81,%82,%83,%84,%85,%86,%87,%88,%89,%90,%91,%92,%93,%94,%95," \
             "%96,%97,%98,%99,%100,%101,%102,%103,%104,%105,%106,%107,%108,%109,%110,%111,%112,%113,%114,%115,%116,%117,%118,%119,%120,%121,%122,%123,%124,%125,%126,%127}"
#define R128(d, e) R8(d, 0), R8(d, 8), R8(d, 16), R8(d, 24), R8(d, 32), R8(d, 40), R8(d, 48), R8(d, 56), \
                   R8(e, 0), R8(e, 8), R8(e, 16), R8(e, 24), R8(e, 32), R8(e, 40), R8(e, 48), R8(e, 56)
__device__ __forceinline__ void mma256_ss(float (&d)[64], float (&e)[64], uint64_t da, uint64_t db, int sc) {
  asm volatile("{\n.reg .pred p;\nsetp.ne.b32 p, %130, 0;\n"
               "wgmma.mma_async.sync.aligned.m64n256k16.f32.bf16.bf16 " D128 ", %128, %129, p, 1, 1, 0, 1;\n}"
               : R128(d, e) : "l"(da), "l"(db), "r"(sc));
}
__device__ __forceinline__ void mma256_rs(float (&d)[64], float (&e)[64], uint32_t a0, uint32_t a1, uint32_t a2, uint32_t a3, uint64_t db) {
  asm volatile("{\n.reg .pred p;\nsetp.ne.b32 p, 1, 0;\n"
               "wgmma.mma_async.sync.aligned.m64n256k16.f32.bf16.bf16 " D128 ", {%128,%129,%130,%131}, %132, p, 1, 1, 1;\n}"
               : R128(d, e) : "r"(a0), "r"(a1), "r"(a2), "r"(a3), "l"(db));
}
template <int N> __device__ __forceinline__ void keep(float (&a)[N]) {
#pragma unroll
  for (int i = 0; i < N; i++) asm volatile("" : "+f"(a[i])::"memory");
}
template <int N> __device__ __forceinline__ void keep(uint32_t (&a)[N]) {
#pragma unroll
  for (int i = 0; i < N; i++) asm volatile("" : "+r"(a[i])::"memory");
}

#define STAMP(idx) do {} while (0)
#define PROF(grp, cond, idx) do {} while (0)

constexpr float SCL2 = 1.4426950408889634f * 0.08838834764831845f;

__device__ __forceinline__ void pack_p(const float (&s)[64], uint32_t (&p)[32]) {
#pragma unroll
  for (int i = 0; i < 32; i++) p[i] = pack_bf(s[2 * i], s[2 * i + 1]);
}

__device__ __forceinline__ void issue_qk(float (&s)[64], uint32_t q0, uint32_t q1, uint32_t kslot) {
  const uint64_t db = make_desc(kslot, 16, 1024), da0 = make_desc(q0, 16, 1024), da1 = make_desc(q1, 16, 1024);
#pragma unroll
  for (int kk = 0; kk < 8; kk++) mma_ss<0>(s, (kk < 4 ? da0 : da1) + (kk & 3) * 2, db + (kk >> 2) * 1024 + (kk & 3) * 2, kk != 0);
}
__device__ __forceinline__ void issue_pv(float (&o)[64], uint32_t (&p)[32], uint32_t vslot, int acc) {
  uint64_t db = make_desc(vslot, 16384, 1024);
#pragma unroll
  for (int kk = 0; kk < 8; kk++)
    mma_rs<1>(o, p[4 * kk], p[4 * kk + 1], p[4 * kk + 2], p[4 * kk + 3], db + kk * 128, kk == 0 ? acc : 1);
}

template <int H>
__device__ __forceinline__ void store_chunk(const float (&a)[64], uint32_t addr) {
#pragma unroll
  for (int i = 8 * H; i < 8 * H + 8; i += 2)
    stmatrix4(addr ^ ((i & 7) << 4), pack_bf(a[4 * i], a[4 * i + 1]), pack_bf(a[4 * i + 2], a[4 * i + 3]),
              pack_bf(a[4 * i + 4], a[4 * i + 5]), pack_bf(a[4 * i + 6], a[4 * i + 7]));
}
template <int H>
__device__ __forceinline__ void store_chunk(const float (&a)[64], float i0, float i1, uint32_t addr) {
#pragma unroll
  for (int i = 8 * H; i < 8 * H + 8; i += 2)
    stmatrix4(addr ^ ((i & 7) << 4), pack_bf(a[4 * i] * i0, a[4 * i + 1] * i0), pack_bf(a[4 * i + 2] * i1, a[4 * i + 3] * i1),
              pack_bf(a[4 * i + 4] * i0, a[4 * i + 5] * i0), pack_bf(a[4 * i + 6] * i1, a[4 * i + 7] * i1));
}
__device__ __forceinline__ float inv_quad_sum(float l) {
  l += __shfl_xor_sync(0xffffffffu, l, 1);
  l += __shfl_xor_sync(0xffffffffu, l, 2);
  return rcp(l);
}

__device__ __forceinline__ void write_table(uint32_t table, bool ca, uint32_t t, const uint4& m0, const uint4& m1) {
  float c0 = untag_sum(m0.x, m1.x), c1 = untag_sum(m0.y, m1.y), c2 = untag_sum(m0.z, m1.z), c3 = untag_sum(m0.w, m1.w);
  if (ca) { c0 = 1.f + rbf(c0); c1 = 1.f + rbf(c1); c2 = 1.f + rbf(c2); c3 = 1.f + rbf(c3); }
  const uint32_t d = table + (t >> 2) * 64 + (t & 1) * 32 + (t & 2) * 2 + (ca ? 0 : 8);
  sts1(d, pack_bf(c0, c1));
  sts1(d + 16, pack_bf(c2, c3));
}

__device__ __forceinline__ void ln_scalars(float mean, float var, float& mb, float& sd) {
  mb = rbf(mean);
  float r; asm("sqrt.approx.ftz.f32 %0, %1;" : "=f"(r) : "f"(rbf(rbf(var) + 1e-5f)));
  sd = rbf(r);
}

__global__ void __cluster_dims__(2, 1, 1) __launch_bounds__(384, 1) fused_kernel(const __grid_constant__ Maps maps, const Ptrs P) {
  extern __shared__ __align__(1024) uint8_t smem_raw[];
  const uint32_t base = smem_u32(smem_raw);
  const int tid = threadIdx.x, lane = tid & 31;
  const int warp = __shfl_sync(0xffffffffu, tid >> 5, 0);
  const int b = blockIdx.x;
  PROF(31, tid == 0, 0);

  if (b >= NMAIN) {
    float* sc = reinterpret_cast<float*>(smem_raw);
    float* red = sc + DM;
    for (int k = tid; k < DM; k += 384) sc[k] = rbf(silu_f(__bfloat162float(P.c[k])));
    __syncthreads();
    if (tid < 256) {
      const int col = 2048 + (b - NMAIN) * 1024 + (tid & 127) * 8, r0 = (tid >> 7) * 512;
      float acc[8];
#pragma unroll
      for (int e = 0; e < 8; e++) acc[e] = 0.f;
#pragma unroll 1
      for (int r = r0; r < r0 + 512; r += HU) {
        uint4 w[HU];
#pragma unroll
        for (int u = 0; u < HU; u++) w[u] = ldg_stream4(P.w_mod + (size_t)(r + u) * NMOD + col);
#pragma unroll
        for (int u = 0; u < HU; u++) {
          float s = sc[r + u];
          acc[0] += s * bf_lo(w[u].x); acc[1] += s * bf_hi(w[u].x); acc[2] += s * bf_lo(w[u].y); acc[3] += s * bf_hi(w[u].y);
          acc[4] += s * bf_lo(w[u].z); acc[5] += s * bf_hi(w[u].z); acc[6] += s * bf_lo(w[u].w); acc[7] += s * bf_hi(w[u].w);
        }
      }
      if (tid >= 128) {
#pragma unroll
        for (int e = 0; e < 8; e++) red[(tid & 127) * 8 + e] = acc[e];
      }
      const uint32_t tag = ld_relaxed(&g_epoch) % 3 + 1;
      bar_sync(1, 256);
      if (tid < 128) {
        uint32_t o[8];
#pragma unroll
        for (int e = 0; e < 8; e++) o[e] = __float_as_uint(rbf(acc[e] + red[tid * 8 + e])) | tag;
        st_relaxed4(g_mod + col, o[0], o[1], o[2], o[3]);
        st_relaxed4(g_mod + col + 4, o[4], o[5], o[6], o[7]);
        const uint4 wr = ldg_nc4(P.w_r + tid * 8);
        const uint32_t wv[4] = {wr.x, wr.y, wr.z, wr.w};
        float dsum = 0.f;
#pragma unroll
        for (int e = 0; e < 8; e++) {
          const float m = bf_hi(o[e]);
          dsum += (b == NMAIN + 2 ? rbf(1.f + m) : m) * ((e & 1) ? bf_hi(wv[e >> 1]) : bf_lo(wv[e >> 1]));
        }
#pragma unroll
        for (int k = 16; k > 0; k >>= 1) dsum += __shfl_xor_sync(0xffffffffu, dsum, k);
        if (lane == 0) st_relaxed(g_mod + (b - NMAIN) * 4 + warp, tagf(dsum, tag));
      }
    }
    PROF(2, tid == 0, 1);
    return;
  }

  const int rank = b & 1;
  const int rb = ((b >> 4) << 1) | rank, cj = (b >> 1) & 7;
  const bool late = b & 4;
  const uint32_t bfull = base + OFF_BAR, bempty = bfull + NSLOT * 8;
  const uint32_t gfull = bempty + NSLOT * 8, gempty = gfull + 32;
  const uint32_t bar_ofull = gempty + 32;
  const uint32_t bar_ofree = bar_ofull + 32;
  const uint32_t bar_par = bar_ofree + 32;
  const uint32_t bar_mod = bar_par + 8;
  const uint32_t bar_pread = bar_mod + 8;
  const uint32_t bar_xres = bar_pread + 8;
  const uint32_t bar_ring = bar_xres + 8;
  const uint32_t bar_box = bar_ring + 24;
  const uint32_t bar_go = bar_box + 96;
  const uint32_t bar_go2 = bar_go + 16;
  const uint32_t bar_cnt = bar_go + 24;
  const uint32_t xfull = bar_go + 40, xempty = xfull + 32;
  const uint32_t bar_hw = xempty + 32, bar_hx = bar_hw + 8;
  const uint32_t bar_hpub = bar_hx + 16;
  const uint32_t bar_win = bar_hpub + 16;
  const uint32_t bar_rx = bar_win + 8;
  const uint32_t bar_sel = bar_rx + 8;
  const uint32_t bar_gate = bar_sel + 8;
  const uint32_t bar_rel = bar_gate + 8;
  const uint32_t bar_od = bar_rel + 8;
  const uint32_t bar_mod2 = bar_od + 8;
  const uint32_t bar_res = bar_go + 8;
  const uint32_t stage = base + OFF_STAGE, par = base + OFF_PAR;

  if (warp == 10 && elect_one()) prefetch_map(&maps.wm);
  if (warp == 8 && elect_one()) {
    for (int s = 0; s < NSLOT; s++) { mbar_init(bfull + s * 8, 1); mbar_init(bempty + s * 8, 16); }
    for (int s = 0; s < 4; s++) { mbar_init(gfull + s * 8, 1); mbar_init(gempty + s * 8, 16); mbar_init(xfull + s * 8, 1); mbar_init(xempty + s * 8, 8); mbar_init(bar_ofree + s * 8, 1); mbar_init(bar_ofull + s * 8, 128); }
    mbar_init(bar_par, 64); mbar_init(bar_mod, 256); mbar_init(bar_pread, 2); mbar_init(bar_xres, 1);
    mbar_init(bar_ring, 8); mbar_init(bar_ring + 8, 8); mbar_init(bar_ring + 16, 8);
    mbar_init(bar_go, 1); mbar_init(bar_go2, 1); mbar_init(bar_cnt, 1); mbar_init(bar_cnt + 8, 1); mbar_init(bar_hpub, 8); mbar_init(bar_hpub + 8, 8); mbar_init(bar_res, 1); mbar_init(bar_win, 1); mbar_init(bar_rx, 1); mbar_init(bar_sel, 64); mbar_init(bar_gate, 8); mbar_init(bar_rel, 8); mbar_init(bar_od, 1); mbar_init(bar_mod2, 64);
    for (int s = 0; s < 12; s++) mbar_init(bar_box + s * 8, 1);
    asm volatile("fence.mbarrier_init.release.cluster;" ::: "memory");
    prefetch_map(&maps.x); prefetch_map(&maps.wq); prefetch_map(&maps.k); prefetch_map(&maps.v);
  }
  if (warp == 9 && elect_one()) {
    mbar_init(bar_hw, 1); mbar_init(bar_hx, 1); mbar_init(bar_hx + 8, 1);
    asm volatile("fence.mbarrier_init.release.cluster;" ::: "memory");
    mbar_expect_tx(bar_hw, 32768);
    mbar_expect_tx(bar_hx, 16384);
    mbar_expect_tx(bar_hx + 8, 16384);
    const __nv_bfloat16* xs = P.x + (size_t)(rb * 128 + cj * 16) * DM;
    bulk_load(base + 2 * GST_BYTES, xs, 16384, bar_hx);
    if (!late) {
      tma2d(stage, &maps.wm, (b >> 1) * 32, rank * 512, bar_hw);
      tma2d(stage + 16384, &maps.wm, (b >> 1) * 32, rank * 512 + 256, bar_hw);
    }
    bulk_load(base + 3 * GST_BYTES, xs + 8 * DM, 16384, bar_hx + 8);
  }
  cluster_arrive();

  if (warp >= 8) {
    asm volatile("setmaxnreg.dec.sync.aligned.u32 40;");
    if (warp < 10) bar_arrive(1, 320);
    const uint32_t epoch = ld_relaxed(&g_epoch);
    cluster_wait();
    if (warp == 8) {
      const int kvrow = (cj >> 1) * SK + (SK - WIN);
      int wch = cj * 8 + rank * 2;
#pragma unroll 1
      for (int ps = 0; ps < 3; ps++) {
        const CUtensorMap* mw = ps == 2 ? &maps.wo : &maps.wq;
        const uint32_t xt = ps == 1 ? XT1 : XT2, wt = ps == 0 ? WT0 : (ps == 1 ? WT1 : WT2);
        const int nst = ps == 2 ? 32 : 16;
#pragma unroll 1
        for (int i = 0; i < nst; i++) {
          const uint32_t bf = gfull + (i & 3) * 8;
          const int kt = ps == 2 ? (((cj & 1) * 4 + ((i >> 1) & 3)) * 4 + (i >> 3)) * 2 + (i & 1) : (ps ? i : slice_of(i) + (b & 14)) & 15;
          const uint32_t wd = base + unit_of(wt, i & 3) + rank * UNIT, xd = base + unit_of(xt, i & 3);
          const uint8_t* xs = g_act + (uint32_t)(rb * 80 + (ps - 1) * 16 + kt) * UNIT;
          if (ps == 0 && i == HD) mbar_wait(bar_mod, 0);
          const bool xfirst = ps && i < 2;
          if (ps == 2 && i == 0) mbar_wait(bar_ofree + 24, 0);
          if (i == 0) fence_async();
          mbar_wait(gempty + (i & 3) * 8, ((i >> 2) & 1) ^ 1);
          if (elect_one()) {
            mbar_expect_tx(bf, ps ? GST_BYTES : 2 * UNIT);
            if (xfirst) bulk_load_stream(xd, xs, UNIT, bf);
          }
          if (ps && i < 4) mbar_wait(bempty + i * 8, 1);
          if (elect_one()) tma3d_mc<true>(wd, mw, 0, (i == 31 ? kt ^ (rank * 32) : kt) * 64, i == 31 ? cj * 2 : wch, bf);
          if (ps) {
            if (i == 16 || i == 24) { mbar_wait(bar_cnt + i - 16, 0); fence_async(); }
            if (i == RES0) mbar_wait(bar_res, 0);
            if (i == 2) mbar_wait(bar_ofree + (ps - 1) * 16, 0);
            if (elect_one()) {
              if (i == 31) bulk_load(xd, xs, UNIT, bf); else if (!xfirst) bulk_load_stream(xd, xs, UNIT, bf);
              mbar_arrive_pred(bar_go, i == GOST - 1);
              if (PG0 < 16) mbar_arrive_pred(bar_go2, ps == 1 && i == PG0);
              mbar_arrive_pred(bar_od, i == (ps == 1 ? ODS1 : ODS));
              if (i == RES0) mbar_expect_tx(bar_xres, 32768);
              if (i == RES0 || i == RES1) tma2d(base + OFF_RES + (i == RES1) * UNIT, &maps.x, cj * 128 + (i == RES1) * 64, rb * 128, bar_xres);
            }
          }
        }
        if (ps == 2) break;
        wch = ps ? ((wch >> 3) ^ rank) * 2 : wch + 4;
#pragma unroll 1
        for (int u = 0; u < 16; u++) {
          const bool isk = (u == 0) || ((u & 1) && u < 15);
          const int blk = (isk ? (u + 1) >> 1 : (u == 15 ? 7 : (u >> 1) - 1)) & 3;
          const uint32_t sl = base + unit_of(ps ? AT1 : AT0, u & 3) + rank * UNIT, bf = bfull + (u & 3) * 8;
          if (u < 4) mbar_wait(gempty + ((u + 1) >> 1) * 8, 1);
          mbar_wait(bempty + (u & 3) * 8, ((u >> 2) & 1) ^ 1);
          if (elect_one()) {
            mbar_arrive_pred(bar_go2, ps && u + 16 == PG0);
            mbar_expect_tx(bf, SLOT_BYTES);
            tma3d_mc<false>(sl, isk ? &maps.k : &maps.v, 0, kvrow + blk * 128, rank, bf);
          }
        }
      }
      if (elect_one()) mbar_expect_tx(bar_rx, UNIT);
      mbar_wait(bar_rel, 0);
      if (elect_one()) {
        bulk_load_stream(base + UNIT, g_act + (uint32_t)(rb * 80 + 16 + 63 - (cj & 1) * 32) * UNIT, UNIT, bar_rx);
      }
      if (b < NFFN) {
#pragma unroll 1
        for (int u = 0; u < 12; u++) {
          const uint32_t dst = base + unit_of(u < 4 ? FT_G : (u < 8 ? FT_U : FT_D), u & 3);
          if (elect_one()) mbar_expect_tx(bar_box + u * 8, UNIT);
          if (u == FB0 || u == FB1 || u == FB2) mbar_wait(bar_ring + (u == FB2 ? 16 : u == FB1 ? 8 : 0), 0);
          const int fp = u < FPB ? FPACE0 : FPACE;
          if (u >= fp) mbar_wait(bar_box + (u - fp) * 8, 0);
          if (elect_one()) {
            if (u < 8) tma2d(dst, u < 4 ? &maps.wg : &maps.wu, b * 32, (u & 3) * 256, bar_box + u * 8);
            else tma3d(dst, &maps.wd, 0, b * 32, (u - 8) * 4, bar_box + u * 8);
          }
        }
      }
    } else if (warp == 9) {
      const uint32_t target = 8 * (epoch + 1);
      uint32_t hmask = 0;
#pragma unroll 1
      for (int i = 0; i < 16; i++) {
        if (i == HDX) mbar_wait(bar_mod, 0);
        const int kt = (2 * cj + slice_of(i)) & 15;
        const uint32_t need = i == 15 ? 0xffffu : 1u << kt;
        if (i >= NRS && (hmask & need) != need) {
          uint32_t n = 0;
          do { hmask = __ballot_sync(0xffffffffu, ld_acquire(&g_cnt_h[rb * 32 + (lane & 15)]) == epoch + 1); watchdog(n); } while ((hmask & need) != need);
          PROF(1, lane == 0 && i == NRS, 26);
          fence_async();
        }
        mbar_wait(xempty + (i & 3) * 8, ((i >> 2) & 1) ^ 1);
        if (elect_one()) {
          mbar_expect_tx(xfull + (i & 3) * 8, UNIT);
          if (i < NRS) tma2d(base + (i & 3) * GST_BYTES, &maps.x, kt * 64, rb * 128, xfull + (i & 3) * 8);
          else bulk_load_stream(base + (i & 3) * GST_BYTES, g_act + (uint32_t)(rb * 80 + kt) * UNIT, UNIT, xfull + (i & 3) * 8);
        }
      }
      prefetch_map(&maps.wo);
#pragma unroll 1
      for (int t = 0; t < 4; t++) {
        if (t & 1) mbar_wait(bar_od, t >> 1);
#pragma unroll 1
        for (int p = 0; p < 32768 / OPS; p++) {
          const uint32_t w = p / (16384 / OPS), c = (p / (8192 / OPS)) & 1, off = w * 8192 + (p % (8192 / OPS)) * OPS;
          mbar_wait(bar_ofull + (t & 1) * 16 + w * 8, t >> 1);
          if (elect_one()) {
            bulk_store(g_act + (uint32_t)(rb * 80 + 16 + (cj * 4 + t) * 2 + c) * UNIT + off, base + unit_of(QT, 2 * t + c) + off, OPS);
            asm volatile("cp.async.bulk.commit_group;" ::: "memory");
            asm volatile("cp.async.bulk.wait_group.read %0;" ::"n"(OFL) : "memory");
          }
        }
        if (elect_one()) {
          asm volatile("cp.async.bulk.wait_group.read 0;" ::: "memory");
          mbar_arrive(t < 3 ? bar_ofree + t * 8 : bar_res);
          asm volatile("cp.async.bulk.wait_group 0;" ::: "memory");
          fence_async();
          red_release(&g_cnt_o[((rb * 4 + t) * 2 + (cj >> 2)) * 32], 2);
        }
        if (t) {
          wait_counter(&g_cnt_o[(rb * 8 + 2 * t + (cj & 1)) * 32], target);
          if (t & 1) wait_counter(&g_cnt_o[(rb * 8 + (t == 1 ? cj & 1 : 7 - (cj & 1))) * 32], target);
          if (elect_one()) mbar_arrive(t == 1 ? bar_ofree + 24 : bar_cnt + t * 8 - 16);
        }
      }
      PROF(2, lane == 0, 27);
      const uint32_t tag = epoch % 3 + 1;
      const uint32_t* inbox = g_cand + (b >> 1) % CR * 512 + (lane & 15) * CS;
      mbar_wait(bar_ring + 16, 0);
      uint32_t c0 = ld_relaxed(inbox), n = 0;
#define CAND_STEP(cv)                                                                                        \
      {                                                                                                      \
        const bool valid = (cv & 3u) == tag, all = __all_sync(0xffffffffu, valid);                           \
        const uint32_t best = __reduce_max_sync(0xffffffffu, valid ? cv : 0u);                               \
        const uint32_t blk = __ffs(__ballot_sync(0xffffffffu, cv == best)) - 1;                              \
        if (best) sts2(par + PAR_CONST + 56, best, (blk << 7 | (~best >> 2 & 127)) | (all ? 0x1800 : 0x800)); \
        if (all) break;                                                                                      \
        cv = ld_relaxed(inbox);                                                                              \
      }
      while (true) { CAND_STEP(c0) watchdog(n); }
    } else {
      const int t2 = tid - 320;
      if (late && warp == 10) {
        mbar_wait(bar_hx, 0);
        if (elect_one()) {
          tma2d(stage, &maps.wm, (b >> 1) * 32, rank * 512, bar_hw);
          tma2d(stage + 16384, &maps.wm, (b >> 1) * 32, rank * 512 + 256, bar_hw);
        }
      }
      {
        const uint32_t tag = epoch % 3 + 1;
        mbar_wait(bar_hx + 8, 0);
        mbar_wait(bar_hw, 0);
        __nanosleep(late ? OSL2 : OSL);
        {
          const uint32_t t7 = (warp & 1) * 64 + (lane >> 4) * 32 + 16 + (lane & 15);
          const uint32_t* pm = g_modp + ((cj * 128 + t7 * 4) & (DM - 1));
          uint4 m0, m1, m2, m3;
          uint32_t n = 0;
          do {
            m0 = ld_relaxed4(pm); m1 = ld_relaxed4(pm + 2 * DM); m2 = ld_relaxed4(pm + DM); m3 = ld_relaxed4(pm + 3 * DM);
            watchdog(n);
          } while (!__all_sync(0xffffffffu, tag_ok(m0, tag) && tag_ok(m1, tag) && tag_ok(m2, tag) && tag_ok(m3, tag)));
          write_table(par, false, t7, m0, m1);
          write_table(par, true, t7, m2, m3);
          mbar_arrive(bar_mod2);
        }
      }
      mbar_wait(bar_hpub + (warp & 1) * 8, 0);
      PROF(1, t2 == 0, 24);
#pragma unroll 1
      for (int c = 0; c < 8; c++) {
        const uint32_t off = (warp & 1) * UNIT + c * 2048 + lane * 16;
        uint8_t* dst = g_act + (uint32_t)(rb * 80 + cj * 2) * UNIT + off;
        const uint4 v0 = lds4(stage + off), v1 = lds4(stage + off + 512), v2 = lds4(stage + off + 1024), v3 = lds4(stage + off + 1536);
        stg4(dst, v0); stg4(dst + 512, v1); stg4(dst + 1024, v2); stg4(dst + 1536, v3);
      }
      __syncwarp();
      PROF(1, t2 == 0, 15);
      if (lane == 0) {
        mbar_arrive(bar_pread);
        red_release(&g_cnt_h[rb * 32 + cj * 2 + (warp & 1)], 1);
        PROF(1, t2 == 0, 25);
        prefetch_map(&maps.wg); prefetch_map(&maps.wu); prefetch_map(&maps.wd); prefetch_map(&maps.out);
      }
      __syncwarp();
      if (b < NFFN) {
        mbar_wait(bar_go2, 0);
        const __nv_bfloat16* pg = ((b & 1) ? P.w_up : P.w_gate) + (b >> 1) * 64 + (size_t)t2 * FF;
        const __nv_bfloat16* pd = P.w_down + (size_t)b * 32768 + t2 * 64;
        PROF(2, t2 == 0, 13);
#pragma unroll 1
        for (int i = 0; i < WN; i += WB) {
          uint32_t v[WB];
#pragma unroll
          for (int u = 0; u < WB; u++) {
            const int k = i + u;
            asm volatile("ld.global.cg.L2::128B.u32 %0, [%1];" : "=r"(v[u]) : "l"(k < 16 ? pg + (size_t)k * 64 * FF : pd + (k - 16) * 4096));
          }
#pragma unroll
          for (int u = 1; u < WB; u++) v[0] ^= v[u];
          sts1(par + PAR_SINK + t2 * 4, v[0]);
        }
        PROF(2, t2 == 0, 14);
      }
      const uint32_t tag = epoch % 3 + 1;
      mbar_wait(bar_go, 0);
      bar_sync(4, 64);
      if (warp == 10) {
        const uint32_t* src = g_mod + 2 * DM + cj * 128 + lane * 4;
        const uint2 wr = *reinterpret_cast<const uint2*>(P.w_r + cj * 128 + lane * 4);
        uint4 vga, vsb, vcb, vgb;
        uint32_t n = 0;
        do {
          vga = ld_relaxed4(src); vsb = ld_relaxed4(src + DM); vcb = ld_relaxed4(src + 2 * DM); vgb = ld_relaxed4(src + 3 * DM);
          watchdog(n);
        } while (!__all_sync(0xffffffffu, tag_ok(vga, tag) && tag_ok(vsb, tag) && tag_ok(vcb, tag) && tag_ok(vgb, tag)));
        const float c0 = rbf(1.f + bf_hi(vcb.x)), c1 = rbf(1.f + bf_hi(vcb.y)), c2 = rbf(1.f + bf_hi(vcb.z)), c3 = rbf(1.f + bf_hi(vcb.w));
        const float a0 = c0 * bf_lo(wr.x), a1 = c1 * bf_hi(wr.x), a2 = c2 * bf_lo(wr.y), a3 = c3 * bf_hi(wr.y);
        const uint32_t h0 = pack_bf(a0, a1), h1 = pack_bf(a2, a3);
        const uint32_t t1 = par + PAR_T1 + (lane >> 2) * 64 + (lane & 1) * 32 + (lane & 2) * 2;
        sts1(t1, h0); sts1(t1 + 8, pack_bf(a0 - bf_lo(h0), a1 - bf_hi(h0)));
        sts1(t1 + 16, h1); sts1(t1 + 24, pack_bf(a2 - bf_lo(h1), a3 - bf_hi(h1)));
        const uint32_t tg = par + PAR_SINK + (lane >> 3) * 64 + (lane & 1) * 32 + (lane & 6) * 2;
        sts1(tg, __byte_perm(vga.x, vga.y, 0x7632)); sts1(tg + 16, __byte_perm(vga.z, vga.w, 0x7632));
        sts4(par + PAR_T2 + lane * 32, make_uint4(pack_bf(c0, c1), __byte_perm(vsb.x, vsb.y, 0x7632), __byte_perm(vgb.x, vgb.y, 0x7632), __byte_perm(vga.x, vga.y, 0x7632)));
        sts4(par + PAR_T2 + lane * 32 + 16, make_uint4(pack_bf(c2, c3), __byte_perm(vsb.z, vsb.w, 0x7632), __byte_perm(vgb.z, vgb.w, 0x7632), __byte_perm(vga.z, vga.w, 0x7632)));
      } else {
        const uint4 g = poll4((lane & 8) ? g_mod + 8 - (lane & 1) * 4 : g_mod + 5 * DM + (b >> 4) * 128 + (lane & 7) * 16 + (b & 12), tag);
        sts1(par + PAR_CONST + 60, 0);
        if (lane < 8) sts1(par + PAR_CONST + 16 + lane * 4, (b & 2) ? ((b & 1) ? g.w : g.z) : ((b & 1) ? g.y : g.x));
        else if (lane < 10) sts2(par + PAR_CONST + (lane - 8) * 8, __float_as_uint(untag_sum(g.x, g.y) + untag_sum(g.z, g.w)), epoch);
      }
      __syncwarp();
#pragma unroll 4
      for (int q = 0; q < 32; q++) st_b128(g_xch + ((size_t)b * 8 * 256 + q * 64 + t2) * 4, (epoch & 1) << 16, 0, 0, 0);
      for (int q = 0; q < 2; q++) st_relaxed4(g_stats + ((size_t)cj * SEQ + rb * 128 + q * 64 + t2) * 4, 0, 0, 0, 0);
      if (b < NFFN)
        for (int q = 0; q < 2; q++) st_relaxed4(ypart_slot(b, q * 64 + t2), 0, 0, 0, 0);
      st_relaxed4(g_row + rb * 2 * DM + (t2 >> 5) * DM + cj * 128 + (t2 & 31) * 4, 0, 0, 0, 0);
      __threadfence();
      mbar_arrive(bar_par);
      mbar_wait(bar_gate, 0);
      uint32_t have = 0, n = 0;
      while (true) {
        const uint32_t st = lds1(par + PAR_CONST + 60) >> 7;
        if ((st & 31) != have) {
          const uint32_t* hsrc = g_row + (st & 15) * 2 * DM + t2 * 4;
          uint4 hv[4];
          bool ok = true;
#pragma unroll
          for (int i = 0; i < 4; i++) hv[i] = ld_pairs(hsrc + i * 256);
#pragma unroll
          for (int i = 0; i < 4; i++) {
            sts2(base + ((FT_G >> i * 4) & 15) * UNIT + (warp & 1) * 8192 + 256 + lane * 8, hv[i].x, hv[i].z);
            ok = ok && hv[i].y == tag && hv[i].w == tag;
          }
          have = __all_sync(0xffffffffu, ok) ? st & 31 : 0;
        }
        if ((st ^ have) == 32) break;
        watchdog(n);
      }
      mbar_arrive(bar_sel);
    }
    __syncwarp();
    cluster_arrive();
    {
      const uint32_t tag = epoch % 3 + 1, t3 = tid - 256;
      mbar_wait(bar_win, 0);
      uint2 win = lds2(par + PAR_CONST + 56);
      win.y &= 0x7ff;
      const uint32_t* fsrc = g_row + (win.y >> 7) * 2 * DM + (b >> 4) * 128 + (t3 & 7) * 16 + (b & 6) * 2 + ((b >> 2) & 2);
      const uint32_t* ysrc = ypart_slot(min(t3, NFFN - 1), b);
      uint2 fh = ld_pair(fsrc), fx = ld_pair(fsrc + DM);
      uint4 ya = ld_b128(ysrc);
      const float rwin = __uint_as_float(((int)win.x < 0 ? win.x & 0x7fffffffu : ~win.x) & ~0x1ffu);
      const float rs = rbf(rcp(1.f + __expf(-rbf(rwin))));
      uint32_t n = 0;
      while (__any_sync(0xffffffffu, fh.y != tag || fx.y != tag)) { fh = ld_pair(fsrc); fx = ld_pair(fsrc + DM); watchdog(n); }
      while (true) {
        const bool miss = ((ya.x & 1) | (ya.y & 1) << 1) != tag;
        if (!__any_sync(0xffffffffu, miss)) break;
        if (miss) ya = ld_b128(ysrc);
        watchdog(n);
      }
      PROF(8, t3 == 0, 5);
      float y[8] = {bf_lo(ya.x & ~1u), bf_hi(ya.x), bf_lo(ya.y & ~1u), bf_hi(ya.y), bf_lo(ya.z), bf_hi(ya.z), bf_lo(ya.w), bf_hi(ya.w)};
#pragma unroll
      for (int h = 4; h > 0; h >>= 1) {
        const bool up = lane & (h * 2);
#pragma unroll
        for (int e = 0; e < h; e++) y[e] = (up ? y[e + h] : y[e]) + __shfl_xor_sync(0xffffffffu, up ? y[e] : y[e + h], h * 2);
      }
      y[0] += __shfl_xor_sync(0xffffffffu, y[0], 1);
      if (!(lane & 1)) sts1(par + PAR_RED + 64 + t3 * 2, __float_as_uint(y[0]));
      bar_sync(4, 128);
      if (t3 < 8) {
        float y0 = 0.f;
#pragma unroll
        for (int w7 = 0; w7 < 7; w7++) y0 += __uint_as_float(lds1(par + PAR_RED + 64 + w7 * 32 + t3 * 4));
        const uint32_t gv = lds1(par + PAR_CONST + 16 + t3 * 4);
        const uint32_t upd = hmul2(pack_bf(y0, y0), pack_bf(rs, rs));
        const uint32_t r = hadd2(fx.x, hmul2(__byte_perm(gv, gv, 0x3232), hadd2(fh.x, upd)));
        reinterpret_cast<uint16_t*>(P.out)[(size_t)win.y * DM + (b >> 4) * 128 + t3 * 16 + (b & 15)] = (b & 1) ? r >> 16 : r;
        if (b == 0 && t3 == 0) st_relaxed(&g_epoch, epoch + 1);
      }
      PROF(31, t3 == 0, 36);
    }
    cluster_wait();
  } else {
    const int wg = warp >> 2;

    uint32_t tag;
    {
      uint32_t* const pmod = g_modp + rank * 2 * DM + (b >> 1) * 32 + lane;
      uint32_t* const pln = g_ln1 + (rb * 128 + cj * 16 + warp) * 4;
      uint32_t sc[8];
#pragma unroll
      for (int k = 0; k < 8; k++) sc[k] = ldg_nc1(P.c + rank * 512 + warp * 64 + k * 8 + (lane & 3) * 2);
      const uint32_t epoch = ld_relaxed(&g_epoch);
      if (warp == 0) st_relaxed(pmod, 0);
      if (lane == 0) { st_b128(pln, 0, 0, 0, 0); st_b128(pln + 32, 0, 0, 0, 0); }
      asm volatile("setmaxnreg.inc.sync.aligned.u32 232;");
      bar_sync(1, 320);
#pragma unroll
      for (int k = 0; k < 8; k++) sc[k] = pack_bf(silu_f(bf_lo(sc[k])), silu_f(bf_hi(sc[k])));
      keep(sc);
      tag = epoch % 3 + 1;
#pragma unroll
      for (int part = 0; part < 4; part++) {
        if (!(part & 1)) {
          const uint32_t xa = base + (2 + part / 2) * GST_BYTES + warp * 2048 + lane * 16;
          mbar_wait(bar_hx + part * 4, 0);
          float s0 = 0.f, s1 = 0.f, q0 = 0.f, q1 = 0.f;
#pragma unroll
          for (int q = 0; q < 4; q++) {
            const uint4 xv = lds4(xa + q * 512);
            const uint32_t u[4] = {xv.x, xv.y, xv.z, xv.w};
#pragma unroll
            for (int e = 0; e < 4; e++) { const float lo = bf_lo(u[e]), hi = bf_hi(u[e]); s0 += lo; s1 += hi; q0 += lo * lo; q1 += hi * hi; }
          }
          s0 += s1; q0 += q1;
#pragma unroll
          for (int o = 16; o > 0; o >>= 1) { s0 += __shfl_xor_sync(0xffffffffu, s0, o); q0 += __shfl_xor_sync(0xffffffffu, q0, o); }
          const float mean = s0 * (1.f / DM);
          float mb, sd;
          ln_scalars(mean, fmaxf(q0 * (1.f / DM) - mean * mean, 0.f), mb, sd);
          uint32_t ih, il;
          split_inv(sd, ih, il);
          if (lane == 0) st_b128(pln + part * 16, pack_bf(mb, mb), ih, il, tag);
          PROF(1, tid == 0 && part == 2, 4);
        } else if (late == (part == 3)) {
          const uint32_t fr = (lane & 7) + (lane >> 4) * 8, tq = lane & 3;
          const uint32_t wa = stage + warp * 4096 + fr * 64 + ((((lane >> 3) & 1) ^ ((fr >> 1) & 3)) << 4);
          float d0[4] = {0.f, 0.f, 0.f, 0.f}, d1[4] = {0.f, 0.f, 0.f, 0.f};
          mbar_wait(bar_hw, 0);
#pragma unroll
          for (int ks = 0; ks < 4; ks++) {
            uint32_t w[8];
            ldmatrix4t(wa + ks * 1024, w[0], w[1], w[2], w[3]);
            ldmatrix4t((wa ^ 32) + ks * 1024, w[4], w[5], w[6], w[7]);
            mma16816(d0, w[0], w[1], w[2], w[3], sc[2 * ks], sc[2 * ks + 1]);
            mma16816(d1, w[4], w[5], w[6], w[7], sc[2 * ks], sc[2 * ks + 1]);
          }
          sts1(base + 2 * GST_BYTES + warp * 2048 + (tq * 8 + (lane >> 2)) * 4, __float_as_uint((tq & 2) ? ((tq & 1) ? d1[2] : d1[0]) : ((tq & 1) ? d0[2] : d0[0])));
          bar_sync(1, 256);
          if (warp == 0) {
            float s = 0.f;
#pragma unroll
            for (int w8 = 0; w8 < 8; w8++) s += __uint_as_float(lds1(base + 2 * GST_BYTES + w8 * 2048 + lane * 4));
            st_relaxed(pmod, (__float_as_uint(s) & ~3u) | tag);
          }
          PROF(1, tid == 0, 3);
        }
      }
      cluster_wait();
      if (wg == 1) bar_arrive(2, 256);
    }

    float f0 = 0.f, f1 = 0.f;
    const uint32_t rempty = lane < 2 ? mapa(bempty, lane & 1) : 0;
    constexpr uint32_t GE = NSLOT * 8 + 32;
    float o[64], s[64];
#pragma unroll 1
    for (int ps = 0; ps < 3; ps++) {
      {
        const uint32_t xt = ps == 1 ? XT1 : XT2, wt = ps == 1 ? WT1 : WT2;
        const int nst = ps == 2 ? 28 : 14;
        if (ps == 0) {
          float ga[64], gb[64];
#pragma unroll
          for (int i = 0; i < 64; i++) { ga[i] = 0.f; gb[i] = 0.f; }
          uint32_t a[2][16];
          const uint32_t l = fresh_lane();
          uint32_t fa[4];
#pragma unroll
          for (int kk = 0; kk < 4; kk++) fa[kk] = (base + wg * 8192 + frag_offset(warp)) ^ (kk * 32);
          const uint32_t mt = par + (l & 3) * 16;
          auto fetch = [&](int i, uint32_t (&f)[16], uint32_t z) {
            mbar_wait(xfull + (i & 3) * 8, i >> 2);
#pragma unroll
            for (int kk = 0; kk < 4; kk++) ldmatrix4(fa[kk] + (i & 3) * GST_BYTES + z, f[4 * kk], f[4 * kk + 1], f[4 * kk + 2], f[4 * kk + 3]);
          };
          const bool oddw = warp & 2;
          uint4 r0, r1;
          {
            const uint32_t t7 = (warp & 1) * 64 + (l >> 4) * 32 + (l & 15);
            const uint32_t* pm = g_modp + wg * DM + ((cj * 128 + t7 * 4) & (DM - 1));
            const uint32_t* pr = g_ln1 + (rb * 128 + warp * 16 + (l >> 2)) * 4;
            uint4 m0 = make_uint4(tag, tag, tag, tag), m1 = m0;
            if (!oddw) { m0 = ld_relaxed4(pm); m1 = ld_relaxed4(pm + 2 * DM); }
            r0 = ld_b128(pr); r1 = ld_b128(pr + 32);
            fetch(0, a[0], 0); fetch(1, a[1], 0);
            uint32_t n = 0;
            bool written = false;
#pragma unroll 1
            while (true) {
              uint32_t miss;
              asm volatile("{ .reg .pred p0, p1, p2, p3; .reg .b32 t, u;\n"
                           "lop3.b32 t, %1, %2, %19, 0x7e; lop3.b32 u, %3, %4, %19, 0x7e; or.b32 t, t, u; and.b32 t, t, 3; setp.ne.u32 p0, t, 0;\n"
                           "lop3.b32 t, %5, %6, %19, 0x7e; lop3.b32 u, %7, %8, %19, 0x7e; or.b32 t, t, u; and.b32 t, t, 3; setp.ne.u32 p1, t, 0;\n"
                           "setp.ne.u32 p2, %12, %19; setp.ne.u32 p3, %16, %19;\n"
                           "@p0 ld.relaxed.gpu.global.v4.u32 {%1, %2, %3, %4}, [%17];\n"
                           "@p1 ld.relaxed.gpu.global.v4.u32 {%5, %6, %7, %8}, [%17 + 8192];\n"
                           "@p2 ld.relaxed.gpu.global.v4.u32 {%9, %10, %11, %12}, [%18];\n"
                           "@p3 ld.relaxed.gpu.global.v4.u32 {%13, %14, %15, %16}, [%18 + 128];\n"
                           "or.pred p0, p0, p1; or.pred p2, p2, p3; vote.sync.any.pred p0, p0, 0xffffffff; vote.sync.any.pred p2, p2, 0xffffffff;\n"
                           "selp.u32 t, 1, 0, p0; selp.u32 u, 2, 0, p2; or.b32 %0, t, u; }"
                           : "=r"(miss), "+r"(m0.x), "+r"(m0.y), "+r"(m0.z), "+r"(m0.w), "+r"(m1.x), "+r"(m1.y), "+r"(m1.z), "+r"(m1.w),
                             "+r"(r0.x), "+r"(r0.y), "+r"(r0.z), "+r"(r0.w), "+r"(r1.x), "+r"(r1.y), "+r"(r1.z), "+r"(r1.w)
                           : "l"(pm), "l"(pr), "r"(tag) : "memory");
              if (!(miss & 1) && !written) {
                written = true;
                if (!oddw) write_table(par, wg, t7, m0, m1);
                mbar_arrive(bar_mod);
              }
              if (!miss) break;
              watchdog(n);
            }
          }
          const uint32_t zero = r0.w ^ tag;
          auto normalize = [&](uint32_t (&f)[16]) {
#pragma unroll
            for (int k = 0; k < 16; k += 2) { f[k] = ln_norm(f[k], r0.x, r0.y, r0.z); f[k + 1] = ln_norm(f[k + 1], r1.x, r1.y, r1.z); }
          };
          auto modulate = [&](int i, uint32_t (&f)[16]) {
#pragma unroll
            for (int kk = 0; kk < 4; kk++) {
              const uint4 m = lds4(mt + slice_of(i) * 256 + kk * 64);
              f[4 * kk] = MODUL(f[4 * kk], m.x, m.z); f[4 * kk + 1] = MODUL(f[4 * kk + 1], m.x, m.z);
              f[4 * kk + 2] = MODUL(f[4 * kk + 2], m.y, m.w); f[4 * kk + 3] = MODUL(f[4 * kk + 3], m.y, m.w);
            }
            keep(f);
            mbar_arrive_pred(xempty + (i & 3) * 8, l == 0);
          };
          auto publish = [&](int u, uint32_t (&f)[16]) {
#pragma unroll
            for (int kk = 0; kk < 4; kk++) stmatrix4(fa[kk] + OFF_STAGE + u * UNIT, f[4 * kk], f[4 * kk + 1], f[4 * kk + 2], f[4 * kk + 3]);
            __syncwarp();
            mbar_arrive_pred(bar_hpub + u * 8, l == 0);
          };
          auto multiply = [&](int i, uint32_t (&f)[16]) {
            mbar_wait(gfull + (i & 3) * 8, i >> 2);
            const uint64_t db = make_desc(base + (i & 3) * GST_BYTES + UNIT, 8192, 1024);
            wg_fence();
#pragma unroll
            for (int kk = 0; kk < 4; kk++) mma256_rs(ga, gb, f[4 * kk], f[4 * kk + 1], f[4 * kk + 2], f[4 * kk + 3], db + kk * 128);
            wg_commit();
          };
          auto next = [&](int i, uint32_t (&f)[16]) {
            wg_wait<1>();
            mbar_arrive_cl(rempty, GE + ((i + 2) & 3) * 8);
            uint32_t z = zero;
#pragma unroll
            for (int k = 0; k < 16; k += 2) asm volatile("lop3.b32 %0, %1, %2, %0, 0xA8;" : "+r"(z) : "r"(f[k]), "r"(f[k + 1]));
            fetch(i, f, z);
            normalize(f);
            if (i == 2) { keep(f); mbar_wait(bar_mod2, 0); }
            modulate(i, f); multiply(i, f);
          };
          normalize(a[0]); normalize(a[1]);
          keep(a[0]); keep(a[1]);
          mbar_wait(bar_mod, 0);
          PROF(1, tid == 0, 2);
          modulate(0, a[0]); multiply(0, a[0]); publish(0, a[0]);
          modulate(1, a[1]); multiply(1, a[1]);
#pragma unroll 1
          for (int i = 2; i < NRS; i += 2) {
            next(i, a[0]);
            if (i == 2) publish(1, a[0]);
            next(i + 1, a[1]);
          }
          wg_wait<1>();
          mbar_arrive_cl(rempty, GE + ((NRS + 2) & 3) * 8);
#pragma unroll 1
          for (int i = NRS; i < 14; i++) {
            mbar_wait(xfull + (i & 3) * 8, (i >> 2) & 1);
            mbar_wait(gfull + (i & 3) * 8, (i >> 2) & 1);
            const uint32_t xa = base + (i & 3) * GST_BYTES;
            const uint64_t da = make_desc(xa + wg * 8192, 16, 1024), db = make_desc(xa + UNIT, 8192, 1024);
            if (i == 13) bar_sync(2 + wg, 256);
            wg_fence();
#pragma unroll
            for (int kk = 0; kk < 4; kk++) mma256_ss(ga, gb, da + kk * 2, db + kk * 128, 1);
            wg_commit();
            if (i == 13) bar_arrive(3 - wg, 256);
            wg_wait<1>();
            uint32_t z = zero;
#pragma unroll
            for (int k = 0; k < 16; k += 2) asm volatile("lop3.b32 %0, %1, %2, %0, 0xA8;" : "+r"(z) : "r"(a[1][k]), "r"(a[1][k + 1]));
            mbar_arrive_cl(rempty, GE + ((i + 3) & 3) * 8 + z);
            mbar_arrive_pred(xempty + ((i + 3) & 3) * 8, l == 0 && i != NRS);
          }
          mbar_wait(xfull + 16, 1);
          wg_wait<0>();
          keep(ga); keep(gb);
#pragma unroll
          for (int i = 0; i < 64; i++) {
            asm volatile("mov.b32 %0, %1;" : "=f"(s[i]) : "f"(ga[i]));
            asm volatile("mov.b32 %0, %1;" : "=f"(o[i]) : "f"(gb[i]));
          }
        } else {
          float ga[64], gb[64];
#pragma unroll
          for (int i = 0; i < 64; i++) {
            asm volatile("mov.b32 %0, %1;" : "=f"(ga[i]) : "f"(s[i]));
            asm volatile("mov.b32 %0, %1;" : "=f"(gb[i]) : "f"(o[i]));
          }
#pragma unroll 1
          for (int i = 0; i < nst; i++) {
            mbar_wait(gfull + (i & 3) * 8, (i >> 2) & 1);
            const uint64_t da = make_desc(base + unit_of(xt, i & 3) + wg * 8192, 16, 1024), db = make_desc(base + unit_of(wt, i & 3), 8192, 1024);
            if (i == nst - 1) bar_sync(2 + wg, 256);
            wg_fence();
#pragma unroll
            for (int kk = 0; kk < 4; kk++) mma256_ss(ga, gb, da + kk * 2, db + kk * 128, kk ? 1 : i);
            wg_commit();
            if (i == nst - 1) bar_arrive(3 - wg, 256);
            wg_wait<1>();
            mbar_arrive_cl(rempty, GE + ((i + 3) & 3) * 8, i != 0);
            PROF(4, tid == 0 && (i & 3) == 0, 40 + (ps - 1) * 4 + i / 4);
          }
          wg_wait<0>();
          keep(ga); keep(gb);
#pragma unroll
          for (int i = 0; i < 64; i++) {
            asm volatile("mov.b32 %0, %1;" : "=f"(s[i]) : "f"(ga[i]));
            asm volatile("mov.b32 %0, %1;" : "=f"(o[i]) : "f"(gb[i]));
          }
        }
        mbar_arrive_cl(rempty, GE + (ps == 2 ? 24 : 8));
        if (ps == 2) break;
      }
      const uint32_t qw = base + wg * 8192, qt = QT >> (16 * ps), at = ps ? AT1 : AT0;
      {
        const uint32_t wt = ps ? WT1 : WT0;
        const uint64_t da0 = make_desc(qw + unit_of(qt, 2), 16, 1024), da1 = make_desc(qw + unit_of(qt, 3), 16, 1024);
        const uint64_t db0 = make_desc(base + unit_of(wt, 2), 8192, 1024), db1 = make_desc(base + unit_of(wt, 3), 8192, 1024);
        mbar_wait(gfull + 16, 1);
        bar_sync(2 + wg, 256);
        wg_fence();
#pragma unroll
        for (int kk = 0; kk < 4; kk++) mma_ss<1>(s, da0 + kk * 2, db0 + kk * 128, 1);
        wg_commit();
        mbar_wait(xfull + 24, 1);
        mbar_wait(gfull + 24, 1);
        wg_fence();
#pragma unroll
        for (int kk = 0; kk < 4; kk++) mma_ss<1>(s, da1 + kk * 2, db1 + kk * 128, 1);
        wg_commit();
        bar_arrive(3 - wg, 256);
        mbar_wait(ps == 0 ? bar_pread : bar_ofree + 8, 0);
        wg_wait<0>();
        keep(s);
        PROF(2, tid == 0, 8 + ps * 8);
        uint32_t q[32];
        pack_p(s, q);
#pragma unroll
        for (int i = 0; i < 4; i++) stmatrix4((qw + unit_of(qt, 0) + frag_offset(warp)) ^ (i << 5), q[4 * i], q[4 * i + 1], q[4 * i + 2], q[4 * i + 3]);
        keep(q);
        bar_sync(2 + wg, 256);
        wg_fence();
#pragma unroll
        for (int kk = 0; kk < 8; kk++) mma_ss<1>(o, (kk < 4 ? da0 : da1) + (kk & 3) * 2, (kk < 4 ? db0 : db1) + UNIT / 16 + (kk & 3) * 128, 1);
        wg_commit();
        mbar_wait(bfull, 0);
        wg_fence();
        const uint64_t dk = make_desc(base + unit_of(at, 0), 16, 1024);
#pragma unroll
        for (int kk = 0; kk < 8; kk++) mma_rs<0>(s, q[4 * kk], q[4 * kk + 1], q[4 * kk + 2], q[4 * kk + 3], dk + (kk >> 2) * 1024 + (kk & 3) * 2, kk != 0);
        wg_commit();
        bar_arrive(3 - wg, 256);
#pragma unroll
        for (int i = 4; i < 8; i++) stmatrix4((qw + unit_of(qt, 1) + frag_offset(warp)) ^ ((i & 3) << 5), q[4 * i], q[4 * i + 1], q[4 * i + 2], q[4 * i + 3]);
        wg_wait<1>();
        keep(o);
        mbar_arrive_cl(rempty, GE + 16);
        mbar_arrive_cl(rempty, GE + 24);
        store_chunk<0>(o, qw + unit_of(qt, 2) + frag_offset(warp));
        store_chunk<1>(o, qw + unit_of(qt, 3) + frag_offset(warp));
        wg_wait<0>();
        keep(s);
        mbar_arrive_cl(rempty, 0);
      }
      PROF(4, tid == 0 && ps == 1, 61);
      float l0 = 0.f, l1 = 0.f;
      auto step = [&](auto odd_c, const int j, uint32_t (&pw)[32], uint32_t (&pr)[32]) {
        constexpr bool ODD = decltype(odd_c)::value;
        const bool first = !ODD && (j & 2) == 0, last = ODD && j == 7;
        const uint32_t ph = (j >> 1) & 1;
        float i0, i1, a0, a1;
        const bool so = !ODD && j == 4;
        if (so) { i0 = inv_quad_sum(l0); i1 = inv_quad_sum(l1); l0 = 0.f; l1 = 0.f; }
        bool redo = !ODD && (j | ps) == 0;
        while (true) {
          if (redo) {
            float m0 = fmaxf(s[0], s[1]), m1 = fmaxf(s[2], s[3]);
#pragma unroll
            for (int i = 1; i < 16; i++) { m0 = fmaxf(m0, fmaxf(s[4 * i], s[4 * i + 1])); m1 = fmaxf(m1, fmaxf(s[4 * i + 2], s[4 * i + 3])); }
            m0 = fmaxf(m0, __shfl_xor_sync(0xffffffffu, m0, 1)); m1 = fmaxf(m1, __shfl_xor_sync(0xffffffffu, m1, 1));
            m0 = fmaxf(m0, __shfl_xor_sync(0xffffffffu, m0, 2)); m1 = fmaxf(m1, __shfl_xor_sync(0xffffffffu, m1, 2));
            m0 *= SCL2; m1 *= SCL2;
            if (!first) {
              m0 = fmaxf(m0, f0); m1 = fmaxf(m1, f1);
              const float c0 = ex2(f0 - m0), c1 = ex2(f1 - m1);
              l0 *= c0; l1 *= c1;
              wg_wait<0>();
              keep(o);
#pragma unroll
              for (int i = 0; i < 16; i++) { o[4 * i] *= c0; o[4 * i + 1] *= c0; o[4 * i + 2] *= c1; o[4 * i + 3] *= c1; }
            }
            f0 = m0; f1 = m1;
          }
          float b0 = 0.f, b1 = 0.f;
          a0 = 0.f; a1 = 0.f;
#pragma unroll
          for (int i = 0; i < 16; i++) {
            const float e0 = ex2(fmaf(s[4 * i], SCL2, -f0)), e1 = ex2(fmaf(s[4 * i + 1], SCL2, -f0));
            const float e2 = ex2(fmaf(s[4 * i + 2], SCL2, -f1)), e3 = ex2(fmaf(s[4 * i + 3], SCL2, -f1));
            a0 += e0; b0 += e1; a1 += e2; b1 += e3;
            pw[2 * i] = pack_bf(e0, e1); pw[2 * i + 1] = pack_bf(e2, e3);
            if (i == VREL) {
#pragma unroll
              for (int k = 0; k < 2 * VREL + 2; k++) asm volatile("" : "+r"(pw[k])::"memory");
              mbar_wait(bar_mod, 0);
              wg_wait<0>();
              mbar_arrive_cl(rempty, ODD ? 16 : 0, !redo && (ODD || j));
#pragma unroll
              for (int k = 4 * VREL + 4; k < 64; k++) asm volatile("" : "+f"(s[k])::"memory");
            }
          }
          a0 += b0; a1 += b1;
          if (redo) break;
          redo = __any_sync(0xffffffffu, !(a0 + a1 < 0x1p90f));
          if (first) {
            uint32_t m0 = __ballot_sync(0xffffffffu, a0 > 0x1p-80f), m1 = __ballot_sync(0xffffffffu, a1 > 0x1p-80f);
            m0 |= m0 >> 1; m1 |= m1 >> 1; m0 |= m0 >> 2; m1 |= m1 >> 2;
            redo = redo || (m0 & m1 & 0x11111111u) != 0x11111111u;
          }
          if (!redo) break;
        }
        l0 += a0; l1 += a1;
        keep(pw);
        keep(o);
        if (so) store_chunk<0>(o, i0, i1, qw + unit_of(qt, 0) + frag_offset(warp));
        keep(o);
        if (j == (ODD ? 5 : 0)) { fence_async_smem(); if (ODD) mbar_arrive(bar_ofull + wg * 8); }
        mbar_wait(bfull + (ODD ? 24 : 8), ph);
        bar_sync(2 + wg, 256);
        if (!last) {
          const uint32_t qn = qt >> (j >= 3 ? 8 : 0);
          wg_fence();
          issue_qk(s, qw + unit_of(qn, 0), qw + unit_of(qn, 1), base + unit_of(at, ODD ? 3 : 1));
          wg_commit();
          mbar_wait(bfull + (ODD ? 0 : 16), ODD ? ph ^ 1 : ph);
        }
        if (so) { store_chunk<1>(o, i0, i1, qw + unit_of(qt, 1) + frag_offset(warp)); keep(o); }
        wg_fence();
        issue_pv(o, pw, base + unit_of(at, ODD ? (last ? 3 : 0) : 2), !first);
        wg_commit();
        bar_arrive(3 - wg, 256);
        wg_wait<1>();
        keep(s);
        mbar_arrive_cl(rempty, ODD ? 24 : 8, !last);
        PROF(4, tid == 0 && ps == 1, 51 + j);
      };
      uint32_t pa[32], pb[32];
#pragma unroll 1
      for (int j = 0; j < 8; j += 2) {
        step(std::false_type{}, j, pa, pb);
        step(std::true_type{}, j + 1, pb, pa);
      }
      {
        const float i0 = inv_quad_sum(l0), i1 = inv_quad_sum(l1);
        wg_wait<0>();
        keep(o);
        mbar_arrive_cl(rempty, 24);
        store_chunk<0>(o, i0, i1, qw + unit_of(qt, 2) + frag_offset(warp));
        store_chunk<1>(o, i0, i1, qw + unit_of(qt, 3) + frag_offset(warp));
        fence_async_smem();
        mbar_arrive(bar_ofull + 16 + wg * 8);
      }
      PROF(2, tid == 0, 10 + ps * 8);
    }

    const int ln = fresh_lane(), g = ln >> 2, tq = ln & 3, ct = warp * 32 + ln;
    const bool lane0 = ln == 0;
    const int lrow0 = warp * 16 + g;
    const int grow0 = rb * 128 + lrow0;
    const uint32_t res = base + OFF_RES, trow = res + wg * 8192 + frag_offset(warp);
    uint32_t xr[32];
    uint4 sv[4], own;
    uint32_t* sp[4];
#pragma unroll
    for (int k = 0; k < 4; k++) sp[k] = g_stats + ((((tq >> 1) * 4 + k) ^ cj) * SEQ + grow0 + (tq & 1) * 8) * 4;
    {
      const uint64_t da = make_desc(base + wg * 8192, 16, 1024), db = make_desc(base, 8192, 1024);
      constexpr int U = UNIT / 16;
#define HALF_STAGE(acc, xu, wu) _Pragma("unroll") for (int kk = 0; kk < 4; kk++) mma_ss<1>(acc, da + (xu) * U + kk * 2, db + (wu) * U + kk * 128, 1)
      PROF(10, ct == PT, 19); STAMP(0);
      cluster_arrive();
      mbar_wait(gfull, 1);
      mbar_wait(gfull + 8, 1);
      bar_sync(2 + wg, 256);
      wg_fence();
      HALF_STAGE(o, 7, 1);
      HALF_STAGE(o, 8, 3);
      wg_commit();
      STAMP(16);
      mbar_wait(gfull + 16, 1);
      STAMP(17);
      wg_fence();
      HALF_STAGE(o, 6, 11);
      wg_commit();
      bar_arrive(3 - wg, 256);
      mbar_wait(bar_par, 0);
      uint32_t* xo = g_xch + ((size_t)b * 8 * 256 + ct) * 4;
      const uint32_t* xi = g_xch + ((size_t)(b ^ 2) * 8 * 256 + ct) * 4;
      const uint32_t par1 = (~lds1(par + PAR_CONST + 4) & 1) << 16;
      wg_wait<1>();
      mbar_arrive_pred(bar_rel, lane0);
      wg_wait<0>();
      keep(o);
      mbar_arrive_pred(bar_ring, lane0);
      PROF(8, ct == PT, 20); STAMP(1);
#define SEND(i) st_b128(xo + (i) * 1024, (pack_bf(o[8 * (i)], o[8 * (i) + 1]) & ~0x10000u) | par1, pack_bf(o[8 * (i) + 2], o[8 * (i) + 3]), \
                        pack_bf(o[8 * (i) + 4], o[8 * (i) + 5]), pack_bf(o[8 * (i) + 6], o[8 * (i) + 7]))
#pragma unroll
      for (int i = 0; i < NS1; i++) SEND(i);
      PROF(8, ct == PT, 21); STAMP(2);
      bar_sync(2 + wg, 256);
      wg_fence();
      HALF_STAGE(s, 7, 0);
      HALF_STAGE(s, 8, 2);
      HALF_STAGE(s, 6, 10);
      wg_commit();
      bar_arrive(3 - wg, 256);
      STAMP(18);
      mbar_wait(gfull + 24, 1);
#pragma unroll
      for (int i = NS1; i < 8; i++) SEND(i);
      uint4 v[8];
#pragma unroll
      for (int i = 0; i < LD1; i++) v[i] = ld_b128(xi + i * 1024);
      STAMP(19);
      mbar_wait(bar_xres, 0);
      wg_wait<0>();
      mbar_arrive_pred(bar_ring + 8, lane0);
      bar_sync(2 + wg, 256);
      STAMP(20);
#pragma unroll
      for (int i = LD1; i < LD2; i++) v[i] = ld_b128(xi + i * 1024);
      mbar_wait(bar_xres, 0);
      wg_fence();
      HALF_STAGE(s, 9, 4);
      wg_commit();
      mbar_wait(bar_rx, 0);
      wg_fence();
      HALF_STAGE(s, 1, 5);
      wg_commit();
      bar_arrive(3 - wg, 256);
      STAMP(21);
#pragma unroll
      for (int i = LD2; i < 8; i++) v[i] = ld_b128(xi + i * 1024);
      if (LD2 < 8) mbar_wait(bar_xres, 0);
      wg_wait<0>();
      keep(s);
      mbar_arrive_pred(bar_ring + 16, lane0);
      PROF(10, ct == PT, 23); STAMP(4);
#pragma unroll
      for (int i = 0; i < 16; i += 2) ldmatrix4((trow ^ ((i & 7) << 4)) + (i >> 3) * 16384, xr[2 * i], xr[2 * i + 1], xr[2 * i + 2], xr[2 * i + 3]);
      uint32_t ga[16];
      uint4 bw[8];
#pragma unroll
      for (int i = 0; i < 8; i++) {
        if (!(i & 1)) {
          const uint4 t = lds4(par + PAR_SINK + i * 32 + tq * 16);
          ga[2 * i] = t.x; ga[2 * i + 1] = t.y; ga[2 * i + 2] = t.z; ga[2 * i + 3] = t.w;
        }
        bw[i] = lds4(par + PAR_T1 + i * 64 + tq * 16);
        if (!(g & 1)) { bw[i].x = 0x3f803f80u; bw[i].y = 0x3f803f80u; }
      }
      uint32_t pk[32];
      pack_p(s, pk);
      keep(pk);
      {
        uint32_t n = 0, miss;
        do {
          miss = 0;
#pragma unroll
          for (int i = 0; i < 8; i++) miss |= v[i].x ^ par1;
          miss = __any_sync(0xffffffffu, miss & 0x10000u);
          if (miss) {
#pragma unroll
            for (int i = 0; i < 8; i++)
              asm volatile("{ .reg .pred p; .reg .b32 t; xor.b32 t, %0, %5; and.b32 t, t, 0x10000; setp.ne.u32 p, t, 0;\n"
                           "@p ld.relaxed.gpu.global.v4.u32 {%0, %1, %2, %3}, [%4]; }"
                           : "+r"(v[i].x), "+r"(v[i].y), "+r"(v[i].z), "+r"(v[i].w) : "l"(xi + i * 1024), "r"(par1) : "memory");
          }
          watchdog(n);
        } while (miss);
      }
      PROF(8, ct == PT, 22); STAMP(3);
      float ds[4] = {0.f, 0.f, 0.f, 0.f}, dl[4] = {0.f, 0.f, 0.f, 0.f}, q0[4] = {0.f, 0.f, 0.f, 0.f}, q1[4] = {0.f, 0.f, 0.f, 0.f};
#pragma unroll
      for (int i = 0; i < 8; i++) {
        const uint32_t u0 = hfma2(ga[2 * i], hadd2(pk[4 * i], v[i].x & ~0x10000u), xr[4 * i]);
        const uint32_t u1 = hfma2(ga[2 * i], hadd2(pk[4 * i + 1], v[i].y), xr[4 * i + 1]);
        const uint32_t u2 = hfma2(ga[2 * i + 1], hadd2(pk[4 * i + 2], v[i].z), xr[4 * i + 2]);
        const uint32_t u3 = hfma2(ga[2 * i + 1], hadd2(pk[4 * i + 3], v[i].w), xr[4 * i + 3]);
        xr[4 * i] = u0; xr[4 * i + 1] = u1; xr[4 * i + 2] = u2; xr[4 * i + 3] = u3;
        mma16816(ds, u0, u1, u2, u3, bw[i].x, bw[i].y);
        mma16816(dl, u0, u1, u2, u3, bw[i].z, bw[i].w);
        mma16816(q0, u0, u1, u2, u3, u0, u2);
        mma16816(q1, u0, u1, u2, u3, u1, u3);
      }
      const float sqa = __shfl_sync(0xffffffffu, (g & 1) ? q0[1] : q0[0], g * 4 + (g >> 1));
      const float sqb = __shfl_sync(0xffffffffu, (g & 1) ? q1[3] : q1[2], g * 4 + (g >> 1));
      own = (tq & 1) ? make_uint4(__float_as_uint(ds[2]), __float_as_uint(sqb), __float_as_uint(ds[3] + dl[3]), tag)
                                 : make_uint4(__float_as_uint(ds[0]), __float_as_uint(sqa), __float_as_uint(ds[1] + dl[1]), tag);
      if (tq < 2) st_b128(sp[0], own.x, own.y, own.z, own.w);
#pragma unroll
      for (int k = 0; k < 4; k++) sv[k] = make_uint4(0, 0, 0, 0);
    }
    PROF(8, ct == PT, 29); STAMP(5);
    uint32_t mm, ih, il;
    float rbest;
    uint32_t wf[128];
    const uint32_t frow = (ln & 7) + (ln >> 4) * 8;
    const uint32_t wfo = base + (warp & 1) * 8192 + frow * 64 + ((((ln >> 3) & 1) ^ ((frow >> 1) & 3)) << 4);
#define LOAD_WF(m) _Pragma("unroll") for (int f = 0; f < 16; f++) {                                                   \
      const int r = ((f >> 1) * 4 + (m) * 2 + (f & 1)) * 4;                                                           \
      ldmatrix4t(((wfo + unit_of((m) ? FT_U : FT_G, warp >> 1)) ^ ((f & 1) * 32)) + (f >> 1) * 1024, wf[r], wf[r + 1], wf[r + 2], wf[r + 3]); \
    }
    bool early;
    {
#pragma unroll
      for (int i = 0; i < 16; i += 2) stmatrix4((trow ^ ((i & 7) << 4)) + (i >> 3) * 16384, xr[2 * i], xr[2 * i + 1], xr[2 * i + 2], xr[2 * i + 3]);
      const uint4 cst = lds4(par + PAR_CONST);
      const float A1 = __uint_as_float(cst.x), A2 = __uint_as_float(cst.z);
      uint32_t n = 0;
      early = false;
#pragma unroll 1
      while (true) {
        uint32_t miss;
        asm volatile("{ .reg .pred p0, p1, p2, p3; .reg .b64 u, v; .reg .b128 w;\n"
                     "setp.ge.u32 p0, %22, 2; setp.ne.and.u32 p0, %4, %21, p0; setp.ne.u32 p1, %8, %21; setp.ne.u32 p2, %12, %21; setp.ne.u32 p3, %16, %21;\n"
                     "@p0 ld.relaxed.gpu.global.v4.u32 {%1, %2, %3, %4}, [%17];\n"
                     "@p1 ld.relaxed.gpu.global.v4.u32 {%5, %6, %7, %8}, [%18];\n"
                     "@p2 ld.relaxed.gpu.global.v4.u32 {%9, %10, %11, %12}, [%19];\n"
                     "@p3 ld.relaxed.gpu.global.v4.u32 {%13, %14, %15, %16}, [%20];\n"
                     "or.pred p0, p0, p1; or.pred p2, p2, p3; or.pred p0, p0, p2; vote.sync.any.pred p0, p0, 0xffffffff; selp.u32 %0, 1, 0, p0; }"
                     : "=r"(miss), "+r"(sv[0].x), "+r"(sv[0].y), "+r"(sv[0].z), "+r"(sv[0].w), "+r"(sv[1].x), "+r"(sv[1].y), "+r"(sv[1].z), "+r"(sv[1].w),
                       "+r"(sv[2].x), "+r"(sv[2].y), "+r"(sv[2].z), "+r"(sv[2].w), "+r"(sv[3].x), "+r"(sv[3].y), "+r"(sv[3].z), "+r"(sv[3].w)
                     : "l"(sp[0]), "l"(sp[1]), "l"(sp[2]), "l"(sp[3]), "r"(tag), "r"(tq) : "memory");
        if (!miss) break;
        if (!early && (b >= NFFN || __all_sync(0xffffffffu, mbar_test(bar_box + (warp >> 1) * 8, 0)))) {
          early = true;
          LOAD_WF(0);
          __syncwarp();
          mbar_arrive_pred(bar_gate, lane0);
        }
        watchdog(n);
      }
      const uint4 v0 = tq < 2 ? own : sv[0], v1 = sv[1], v2 = sv[2], v3 = sv[3];
      PROF(8, ct == PT, 30); STAMP(6);
      float su = (__uint_as_float(v0.x) + __uint_as_float(v1.x)) + (__uint_as_float(v2.x) + __uint_as_float(v3.x));
      float sq = (__uint_as_float(v0.y) + __uint_as_float(v1.y)) + (__uint_as_float(v2.y) + __uint_as_float(v3.y));
      float dt = (__uint_as_float(v0.z) + __uint_as_float(v1.z)) + (__uint_as_float(v2.z) + __uint_as_float(v3.z));
      su += __shfl_xor_sync(0xffffffffu, su, 2); sq += __shfl_xor_sync(0xffffffffu, sq, 2); dt += __shfl_xor_sync(0xffffffffu, dt, 2);
      const float m = su * (1.f / DM);
      float mb, sd;
      ln_scalars(m, fmaxf(sq * (1.f / DM) - m * m, 0.f), mb, sd);
      const float inv = rcp(sd);
      rbest = (dt - mb * A1) * inv + A2;
      mm = pack_bf(mb, mb);
      ih = pack_bf(inv, inv);
      const float lo = inv - bf_lo(ih);
      il = pack_bf(lo, lo);
    }
    int ibest;
    {
      const uint32_t bits = __float_as_uint(rbest);
      const uint32_t key = (((int)bits < 0 ? ~bits : bits | 0x80000000u) & ~0x1ffu) | ((127 - lrow0 - (tq & 1) * 8) << 2) | tag;
      sts1(par + PAR_RED + warp * 4, __reduce_max_sync(0xffffffffu, key));
      PROF(8, ct == PT, 38); STAMP(7);
      bar_sync(1, 256);
      const uint4 ka = lds4(par + PAR_RED), kb = lds4(par + PAR_RED + 16);
      const uint32_t k2 = max(max(max(ka.x, ka.y), max(ka.z, ka.w)), max(max(kb.x, kb.y), max(kb.z, kb.w)));
      if (ct < CR && cj == 0) st_relaxed(g_cand + ct * 512 + rb * CS, k2);
      ibest = 127 - ((k2 >> 2) & 127);
    }
    PROF(8, ct == PT, 39); STAMP(8);
    if ((ibest >> 4) == warp) {
      const int src = (ibest & 7) * 4 + ((ibest >> 3) & 1), ch = g * 2;
      const uint32_t cm = __shfl_sync(0xffffffffu, mm, src), ch_ = __shfl_sync(0xffffffffu, ih, src), cl = __shfl_sync(0xffffffffu, il, src);
      const uint32_t xa = res + (ch >> 3) * 16384 + ibest * 128 + (((ch & 7) ^ (ibest & 7)) << 4) + tq * 4;
      const uint32_t x0 = lds1(xa), x1 = lds1(xa ^ 16);
      const uint2 p0 = lds2(par + PAR_T2 + ch * 64 + tq * 16), p1 = lds2(par + PAR_T2 + ch * 64 + 64 + tq * 16);
      uint32_t* dst = g_row + rb * 2 * DM + cj * 128 + ln * 4;
      st_pairs(dst, ln_mod(x0, cm, ch_, cl, p0.x, p0.y), ln_mod(x1, cm, ch_, cl, p1.x, p1.y), tag);
      st_pairs(dst + DM, x0, x1, tag);
      __syncwarp();
    }
    PROF(8, ct == PT, 37); STAMP(9);
    uint32_t wd[64];
    const uint32_t wda = base + unit_of(FT_D, warp >> 1) + (warp & 1) * 8192 + frow * 128 + ((((ln >> 3) & 1) ^ (ln & 7)) << 4);
#define LOAD_WD(f) ldmatrix4t((wda ^ ((((f) >> 1) & 3) * 32)) + ((f) >> 3) * 4096 + ((f) & 1) * 2048, wd[4 * (f)], wd[4 * (f) + 1], wd[4 * (f) + 2], wd[4 * (f) + 3])
    if (!early) {
      if (b < NFFN) mbar_wait(bar_box + (warp >> 1) * 8, 0);
      LOAD_WF(0);
      __syncwarp();
      mbar_arrive_pred(bar_gate, lane0);
    }
    if (b < NFFN) {
      const uint32_t own = base + unit_of(FT_G, warp >> 1) + (warp & 1) * 8192;
      mbar_wait(bar_box + (4 + (warp >> 1)) * 8, 0);
      LOAD_WF(1);
      uint32_t* const ydst = ypart_slot(b, warp * 16 + (tq & 1) * 8 + g);
      PROF(8, ct == PT, 31); STAMP(10);
      bool wdok;
      {
        uint32_t n = 0;
        while (!(wdok = __all_sync(0xffffffffu, mbar_test(bar_box + (8 + (warp >> 1)) * 8, 0))) && !__all_sync(0xffffffffu, mbar_test(bar_sel, 0))) watchdog(n);
      }
      if (wdok) {
#pragma unroll
        for (int f = 0; f < 16; f++) LOAD_WD(f);
      }
      STAMP(11);
      mbar_wait(bar_sel, 0);
      PROF(8, ct == PT, 33); STAMP(12);
      float d[8][4];
#pragma unroll
      for (int i = 0; i < 4; i++) { d[i][0] = 0.f; d[i][1] = 0.f; d[i][2] = 0.f; d[i][3] = 0.f; }
#pragma unroll
      for (int ks = 0; ks < 8; ks++) {
        const uint2 hb = lds2(own + 256 + ks * 32 + tq * 8);
#pragma unroll
        for (int mt = 0; mt < 4; mt++) {
          const int r = ks * 16 + mt * 4;
          mma16816(d[mt], wf[r], wf[r + 1], wf[r + 2], wf[r + 3], hb.x, hb.y);
        }
      }
      sts2(own + (tq * 8 + g) * 8, __float_as_uint((tq & 2) ? ((tq & 1) ? d[1][2] : d[1][0]) : ((tq & 1) ? d[0][2] : d[0][0])),
           __float_as_uint((tq & 2) ? ((tq & 1) ? d[3][2] : d[3][0]) : ((tq & 1) ? d[2][2] : d[2][0])));
      bar_sync(1, 256);
      uint32_t ab[4];
      {
        float G = 0.f, U = 0.f;
        uint2 pv[8];
#pragma unroll
        for (int w8 = 0; w8 < 8; w8++) pv[w8] = lds2(base + ln * 8 + ((FT_G >> (w8 >> 1) * 4) & 15) * UNIT + (w8 & 1) * 8192);
#pragma unroll
        for (int w8 = 0; w8 < 8; w8 += 2) {
          G += __uint_as_float(pv[w8].x) + __uint_as_float(pv[w8 + 1].x);
          U += __uint_as_float(pv[w8].y) + __uint_as_float(pv[w8 + 1].y);
        }
        const float act = rbf(silu_f(rbf(G))) * rbf(U);
        const uint32_t pk = pack_bf(act, __shfl_down_sync(0xffffffffu, act, 1));
#pragma unroll
        for (int i = 0; i < 4; i++) ab[i] = __shfl_sync(0xffffffffu, pk, i * 8 + tq * 2);
      }
      if (!wdok) {
        mbar_wait(bar_box + (8 + (warp >> 1)) * 8, 0);
#pragma unroll
        for (int f = 0; f < 16; f++) LOAD_WD(f);
      }
      PROF(8, ct == PT, 34); STAMP(13);
#pragma unroll
      for (int mt = 0; mt < 8; mt++) {
        d[mt][0] = 0.f; d[mt][1] = 0.f; d[mt][2] = 0.f; d[mt][3] = 0.f;
        mma16816(d[mt], wd[mt * 8], wd[mt * 8 + 1], wd[mt * 8 + 2], wd[mt * 8 + 3], ab[0], ab[1]);
        mma16816(d[mt], wd[mt * 8 + 4], wd[mt * 8 + 5], wd[mt * 8 + 6], wd[mt * 8 + 7], ab[2], ab[3]);
      }
      uint32_t yw[4];
#pragma unroll
      for (int i = 0; i < 4; i++) yw[i] = (tq & 1) ? pack_bf(d[2 * i][2], d[2 * i + 1][2]) : pack_bf(d[2 * i][0], d[2 * i + 1][0]);
      if (tq < 2) st_b128(ydst, (yw[0] & ~1u) | (tag & 1), (yw[1] & ~1u) | (tag >> 1), yw[2], yw[3]);
      PROF(8, ct == PT, 35); STAMP(14);
    }
    mbar_wait(bar_sel, 0);
    mbar_arrive_pred(bar_win, ct == 0);
    const int iwin = lds1(par + PAR_CONST + 60) & 0x7ff;
    const bool cand = (iwin >> 4) == rb * 8 + warp;
    {
      const uint32_t mm0 = __shfl_sync(0xffffffffu, mm, ln & ~1), mm1 = __shfl_sync(0xffffffffu, mm, ln | 1);
      const uint32_t ih0 = __shfl_sync(0xffffffffu, ih, ln & ~1), ih1 = __shfl_sync(0xffffffffu, ih, ln | 1);
      const uint32_t il0 = __shfl_sync(0xffffffffu, il, ln & ~1), il1 = __shfl_sync(0xffffffffu, il, ln | 1);
#pragma unroll 1
      for (int hf = 0; hf < 2; hf++) {
        uint32_t x[16];
#pragma unroll
        for (int i = 0; i < 8; i += 2) ldmatrix4((trow ^ (i << 4)) + hf * 16384, x[2 * i], x[2 * i + 1], x[2 * i + 2], x[2 * i + 3]);
#pragma unroll
        for (int i = 0; i < 8; i++) {
          const uint4 pv = lds4(par + PAR_T2 + (hf * 8 + i) * 64 + tq * 16);
          x[2 * i] = hadd2(x[2 * i], hmul2(pv.z, ln_mod(x[2 * i], mm0, ih0, il0, pv.x, pv.y)));
          x[2 * i + 1] = hadd2(x[2 * i + 1], hmul2(pv.z, ln_mod(x[2 * i + 1], mm1, ih1, il1, pv.x, pv.y)));
        }
#pragma unroll
        for (int i = 0; i < 8; i += 2) stmatrix4((trow ^ (i << 4)) + hf * 16384, x[2 * i], x[2 * i + 1], x[2 * i + 2], x[2 * i + 3]);
      }
      if (!cand) fence_async_smem();
      __syncwarp();
      if (!cand && elect_one()) {
        tma2d_store(&maps.out, res + warp * 2048, cj * 128, rb * 128 + warp * 16);
        tma2d_store(&maps.out, res + 16384 + warp * 2048, cj * 128 + 64, rb * 128 + warp * 16);
        asm volatile("cp.async.bulk.commit_group;" ::: "memory");
      }
    }
    if (cand) {
      const int wrow0 = warp * 16;
#pragma unroll 2
      for (int p = 0; p < 8; p++) {
        const int row = 2 * p + (ln >> 4), ch = ln & 15;
        const uint4 v = lds4(res + (ch >> 3) * 16384 + (wrow0 + row) * 128 + (((ch & 7) ^ (row & 7)) << 4));
        if (rb * 128 + wrow0 + row != iwin) *reinterpret_cast<uint4*>(P.out + (size_t)(rb * 128 + wrow0 + row) * DM + cj * 128 + ch * 8) = v;
      }
    }
    asm volatile("cp.async.bulk.wait_group.read 0;" ::: "memory");
    PROF(8, ct == PT, 11); STAMP(15);
    cluster_wait();
  }
}

typedef CUresult (*EncodeFn)(CUtensorMap*, CUtensorMapDataType, cuuint32_t, void*, const cuuint64_t*, const cuuint64_t*,
                             const cuuint32_t*, const cuuint32_t*, CUtensorMapInterleave, CUtensorMapSwizzle,
                             CUtensorMapL2promotion, CUtensorMapFloatOOBfill);

void map2d(EncodeFn enc, CUtensorMap* m, const void* p, uint64_t rows, uint64_t cols, uint32_t brows) {
  cuuint64_t dims[2] = {cols, rows}, strides[1] = {cols * 2};
  cuuint32_t box[2] = {64, brows}, es[2] = {1, 1};
  enc(m, CU_TENSOR_MAP_DATA_TYPE_BFLOAT16, 2, const_cast<void*>(p), dims, strides, box, es, CU_TENSOR_MAP_INTERLEAVE_NONE,
      CU_TENSOR_MAP_SWIZZLE_128B, CU_TENSOR_MAP_L2_PROMOTION_L2_256B, CU_TENSOR_MAP_FLOAT_OOB_FILL_NONE);
}
void map2d_narrow(EncodeFn enc, CUtensorMap* m, const void* p, uint64_t rows, uint64_t cols, uint32_t brows) {
  cuuint64_t dims[2] = {cols, rows}, strides[1] = {cols * 2};
  cuuint32_t box[2] = {32, brows}, es[2] = {1, 1};
  enc(m, CU_TENSOR_MAP_DATA_TYPE_BFLOAT16, 2, const_cast<void*>(p), dims, strides, box, es, CU_TENSOR_MAP_INTERLEAVE_NONE,
      CU_TENSOR_MAP_SWIZZLE_64B, CU_TENSOR_MAP_L2_PROMOTION_L2_64B, CU_TENSOR_MAP_FLOAT_OOB_FILL_NONE);
}
void map3d(EncodeFn enc, CUtensorMap* m, const void* p, uint64_t rows, uint64_t cols, uint32_t brows, uint32_t nch) {
  cuuint64_t dims[3] = {64, rows, cols / 64}, strides[2] = {cols * 2, 128};
  cuuint32_t box[3] = {64, brows, nch}, es[3] = {1, 1, 1};
  enc(m, CU_TENSOR_MAP_DATA_TYPE_BFLOAT16, 3, const_cast<void*>(p), dims, strides, box, es, CU_TENSOR_MAP_INTERLEAVE_NONE,
      CU_TENSOR_MAP_SWIZZLE_128B, CU_TENSOR_MAP_L2_PROMOTION_L2_256B, CU_TENSOR_MAP_FLOAT_OOB_FILL_NONE);
}

}

extern "C" void kernel_launch(void* const* d_in, const int* in_sizes, int n_in, void* d_out, int out_size) {
  (void)in_sizes; (void)n_in; (void)out_size;
  static EncodeFn enc = nullptr;
  if (!enc) {
    void* fn = nullptr;
    cudaDriverEntryPointQueryResult st;
    cudaGetDriverEntryPoint("cuTensorMapEncodeTiled", &fn, cudaEnableDefault, &st);
    enc = (EncodeFn)fn;
    cudaFuncSetAttribute(fused_kernel, cudaFuncAttributeMaxDynamicSharedMemorySize, SMEM_BYTES);
  }
  Maps maps;
  map2d(enc, &maps.x, d_in[0], SEQ, DM, 128);
  map2d(enc, &maps.out, d_out, SEQ, DM, 16);
  map3d(enc, &maps.wq, d_in[3], DM, NQ, 64, 2);
  map3d(enc, &maps.k, d_in[1], 4 * SK, 128, 128, 1);
  map3d(enc, &maps.v, d_in[2], 4 * SK, 128, 128, 1);
  map3d(enc, &maps.wo, d_in[4], NQ, DM, 64, 2);
  map2d_narrow(enc, &maps.wg, d_in[7], DM, FF, 256);
  map2d_narrow(enc, &maps.wu, d_in[8], DM, FF, 256);
  map3d(enc, &maps.wd, d_in[9], FF, DM, 32, 4);
  map2d_narrow(enc, &maps.wm, d_in[11], DM, NMOD, 256);
  Ptrs p;
  p.x = (const __nv_bfloat16*)d_in[0];
  p.w_r = (const __nv_bfloat16*)d_in[6];
  p.w_gate = (const __nv_bfloat16*)d_in[7];
  p.w_up = (const __nv_bfloat16*)d_in[8];
  p.w_down = (const __nv_bfloat16*)d_in[9];
  p.c = (const __nv_bfloat16*)d_in[10];
  p.w_mod = (const __nv_bfloat16*)d_in[11];
  p.out = (__nv_bfloat16*)d_out;
  fused_kernel<<<NMAIN + NHELP, 384, SMEM_BYTES>>>(maps, p);
}
```

```cpp
#include <cuda_runtime.h>
#include <cuda_bf16.h>
#include <cuda.h>
#include <stdint.h>
#include <type_traits>

#define HD 2
#define HDX 2
#define NRS 8
#define FPACE 3
#define GOST 20
#define WB 2
#define WN 20
#define RES0 17
#define RES1 20
#define HU 32
#define NS1 5
#define PG0 15
#define FB0 0
#define FB2 8
#define OPS 8192
#define OFL 0
#define ODS 8
#define MODUL hfma2
#define ODS1 5
#define LD1 0
#define LD2 4
#define FB1 2
#define FPB 8
#define FPACE0 2
#define OSL 900
#define OSL2 400
#define CR 8
#define CS 8
#define OURV 1
#define VREL 5
#define E0 3

namespace {

constexpr int SEQ = 2048, DM = 1024, NQ = 4096, SK = 2048, WIN = 512, FF = 3584, NMOD = 6144;
constexpr int OUR = OURV;
constexpr int NMAIN = 128, NHELP = 4, NFFN = 112;
constexpr int NSLOT = 4, SLOT_BYTES = 32768, UNIT = 16384, GST_BYTES = 3 * UNIT;
constexpr uint32_t XT1 = 0xDCBA, XT2 = 0x9687;
constexpr uint32_t WT0 = 0xA741, WT1 = 0x7420, WT2 = 0x4A20;
constexpr uint32_t AT0 = WT1, AT1 = WT2;
constexpr uint32_t QT = 0xDC9696DC;
constexpr int OFF_STAGE = 12 * UNIT;
constexpr uint32_t FT_G = 0x07B3, FT_U = 0xA628, FT_D = 0x5149;
constexpr int OFF_RES = 12 * UNIT;
constexpr int OFF_PAR = 14 * UNIT;
constexpr int OFF_BAR = OFF_PAR + 2528;
constexpr int SMEM_BYTES = OFF_BAR + 544;
static_assert(SMEM_BYTES <= 232448, "smem");

constexpr int PAR_T1 = 0;
constexpr int PAR_T2 = 512;
constexpr int PAR_CONST = 1536;
constexpr int PAR_RED = 1600;
constexpr int PAR_SINK = 2176;

struct Maps {
  CUtensorMap x, wq, k, v, wo, wg, wu, wd, wm, out;
};
struct Ptrs {
  const __nv_bfloat16 *x, *w_r, *c, *w_mod, *w_gate, *w_up, *w_down;
  __nv_bfloat16* out;
};

__device__ __align__(1024) uint8_t g_act[16 * 80 * UNIT];
__device__ __align__(128) uint32_t g_mod[NMOD];
__device__ __align__(128) uint32_t g_modp[2 * 2 * DM];
__device__ __align__(128) uint32_t g_ln1[SEQ * 4];
__device__ __align__(128) uint32_t g_cnt_h[16 * 32];
__device__ __align__(128) uint32_t g_cnt_o[128 * 32];
__device__ __align__(128) uint32_t g_xch[NMAIN * 8 * 256 * 4];
__device__ __align__(128) uint32_t g_stats[8 * SEQ * 4];
__device__ __align__(128) uint32_t g_cand[CR * 512];
__device__ __align__(128) uint32_t g_row[16 * 2 * DM];
__device__ __align__(128) uint32_t g_ypart[NMAIN * NFFN * 4];
__device__ __forceinline__ uint32_t* ypart_slot(int writer, int reader) { return g_ypart + (writer * NMAIN + reader) * 4; }
__device__ uint32_t g_epoch;

__device__ __forceinline__ uint32_t fresh_lane() { uint32_t l; asm volatile("mov.u32 %0, %%laneid;" : "=r"(l)); return l; }
__device__ __forceinline__ uint32_t frag_offset(int warp) {
  const uint32_t l = fresh_lane();
  return ((warp & 3) * 16 + (l & 15)) * 128 + (((l >> 4) ^ (l & 7)) << 4);
}
__device__ __forceinline__ bool elect_one() {
  uint32_t p;
  asm volatile("{ .reg .pred q; elect.sync _|q, 0xffffffff; selp.u32 %0, 1, 0, q; }" : "=r"(p));
  return p;
}
__device__ __forceinline__ uint32_t smem_u32(const void* p) { return (uint32_t)__cvta_generic_to_shared(p); }
__device__ __forceinline__ void mbar_init(uint32_t bar, uint32_t cnt) {
  asm volatile("mbarrier.init.shared::cta.b64 [%0], %1;" ::"r"(bar), "r"(cnt) : "memory");
}
__device__ __forceinline__ void mbar_expect_tx(uint32_t bar, uint32_t bytes) {
  asm volatile("mbarrier.arrive.expect_tx.shared::cta.b64 _, [%0], %1;" ::"r"(bar), "r"(bytes) : "memory");
}
__device__ __forceinline__ void mbar_arrive(uint32_t bar) {
  asm volatile("mbarrier.arrive.shared::cta.b64 _, [%0];" ::"r"(bar) : "memory");
}
__device__ __forceinline__ void mbar_arrive_pred(uint32_t bar, bool p) {
  asm volatile("{ .reg .pred p; setp.ne.b32 p, %1, 0; @p mbarrier.arrive.shared::cta.b64 _, [%0]; }" ::"r"(bar), "r"((int)p) : "memory");
}
__device__ __forceinline__ void mbar_arrive_cl(uint32_t bar, uint32_t off, bool p = true) {
  asm volatile("{ .reg .pred p, q; .reg .b32 a; setp.ne.b32 q, %2, 0; setp.ne.and.b32 p, %0, 0, q; add.u32 a, %0, %1; @p mbarrier.arrive.shared::cluster.b64 _, [a]; }"
               ::"r"(bar), "r"(off), "r"((int)p) : "memory");
}
__device__ __forceinline__ uint32_t mapa(uint32_t addr, uint32_t cta) {
  uint32_t r; asm("mapa.shared::cluster.u32 %0, %1, %2;" : "=r"(r) : "r"(addr), "r"(cta)); return r;
}
__device__ __forceinline__ void cluster_arrive() { asm volatile("barrier.cluster.arrive.relaxed.aligned;" ::: "memory"); }
__device__ __forceinline__ void cluster_wait() { asm volatile("barrier.cluster.wait.aligned;" ::: "memory"); }
__device__ __forceinline__ void watchdog(uint32_t& n) {
}
__device__ __forceinline__ void mbar_wait(uint32_t bar, uint32_t parity) {
  asm volatile("{\n.reg .pred p;\nWAIT_%=:\nmbarrier.try_wait.parity.shared::cta.b64 p, [%0], %1;\n@!p bra WAIT_%=;\n}" ::"r"(bar), "r"(parity) : "memory");
}
__device__ __forceinline__ bool mbar_test(uint32_t bar, uint32_t parity) {
  uint32_t ok;
  asm volatile("{\n.reg .pred p;\nmbarrier.test_wait.parity.shared::cta.b64 p, [%1], %2;\nselp.u32 %0, 1, 0, p;\n}" : "=r"(ok) : "r"(bar), "r"(parity) : "memory");
  return ok;
}
__device__ __forceinline__ uint64_t l2_stream() {
  uint64_t f; asm("createpolicy.fractional.L2::evict_first.b64 %0, 1.0;" : "=l"(f)); return f;
}
__device__ __forceinline__ void tma2d(uint32_t dst, const CUtensorMap* m, int c0, int c1, uint32_t bar) {
  asm volatile("cp.async.bulk.tensor.2d.shared::cluster.global.mbarrier::complete_tx::bytes.L2::cache_hint [%0], [%1, {%3, %4}], [%2], %5;"
               ::"r"(dst), "l"(m), "r"(bar), "r"(c0), "r"(c1), "l"(l2_stream()) : "memory");
}
__device__ __forceinline__ void bulk_load(uint32_t dst, const void* src, uint32_t bytes, uint32_t bar) {
  asm volatile("cp.async.bulk.shared::cluster.global.mbarrier::complete_tx::bytes [%0], [%1], %2, [%3];" ::"r"(dst), "l"(src), "r"(bytes), "r"(bar) : "memory");
}
__device__ __forceinline__ void bulk_load_stream(uint32_t dst, const void* src, uint32_t bytes, uint32_t bar) {
  asm volatile("cp.async.bulk.shared::cluster.global.mbarrier::complete_tx::bytes.L2::cache_hint [%0], [%1], %2, [%3], %4;"
               ::"r"(dst), "l"(src), "r"(bytes), "r"(bar), "l"(l2_stream()) : "memory");
}
__device__ __forceinline__ void tma2d_store(const CUtensorMap* m, uint32_t src, int c0, int c1) {
  asm volatile("cp.async.bulk.tensor.2d.global.shared::cta.bulk_group [%0, {%2, %3}], [%1];" ::"l"(m), "r"(src), "r"(c0), "r"(c1) : "memory");
}
__device__ __forceinline__ void bulk_store(void* dst, uint32_t src, uint32_t bytes) {
  asm volatile("cp.async.bulk.global.shared::cta.bulk_group [%0], [%1], %2;" ::"l"(dst), "r"(src), "r"(bytes) : "memory");
}
__device__ __forceinline__ int slice_of(int i) { return i + ((i & 7) == 1) - ((i & 7) == 2); }
__device__ __forceinline__ uint32_t unit_of(uint32_t table, uint32_t i) { return ((table >> (i * 4)) & 15) * UNIT; }
__device__ __forceinline__ void tma3d(uint32_t dst, const CUtensorMap* m, int c0, int c1, int c2, uint32_t bar) {
  asm volatile("cp.async.bulk.tensor.3d.shared::cluster.global.mbarrier::complete_tx::bytes.L2::cache_hint [%0], [%1, {%3, %4, %5}], [%2], %6;"
               ::"r"(dst), "l"(m), "r"(bar), "r"(c0), "r"(c1), "r"(c2), "l"(l2_stream()) : "memory");
}
template <bool STREAM>
__device__ __forceinline__ void tma3d_mc(uint32_t dst, const CUtensorMap* m, int c0, int c1, int c2, uint32_t bar) {
  if (STREAM)
    asm volatile("cp.async.bulk.tensor.3d.shared::cluster.global.mbarrier::complete_tx::bytes.multicast::cluster.L2::cache_hint [%0], [%1, {%3, %4, %5}], [%2], %6, %7;"
                 ::"r"(dst), "l"(m), "r"(bar), "r"(c0), "r"(c1), "r"(c2), "h"((uint16_t)3), "l"(l2_stream()) : "memory");
  else
    asm volatile("cp.async.bulk.tensor.3d.shared::cluster.global.mbarrier::complete_tx::bytes.multicast::cluster [%0], [%1, {%3, %4, %5}], [%2], %6;"
                 ::"r"(dst), "l"(m), "r"(bar), "r"(c0), "r"(c1), "r"(c2), "h"((uint16_t)3) : "memory");
}
__device__ __forceinline__ void prefetch_map(const CUtensorMap* m) {
  asm volatile("prefetch.tensormap [%0];" ::"l"(m) : "memory");
}
__device__ __forceinline__ void fence_async() { asm volatile("fence.proxy.async.global;" ::: "memory"); }
__device__ __forceinline__ void fence_async_smem() { asm volatile("fence.proxy.async.shared::cta;" ::: "memory"); }
__device__ __forceinline__ void bar_sync(int id, int n) { asm volatile("bar.sync %0, %1;" ::"r"(id), "r"(n) : "memory"); }
__device__ __forceinline__ void bar_arrive(int id, int n) { asm volatile("bar.arrive %0, %1;" ::"r"(id), "r"(n) : "memory"); }
__device__ __forceinline__ void wg_fence() { asm volatile("wgmma.fence.sync.aligned;" ::: "memory"); }
__device__ __forceinline__ void wg_commit() { asm volatile("wgmma.commit_group.sync.aligned;" ::: "memory"); }
template <int N> __device__ __forceinline__ void wg_wait() { asm volatile("wgmma.wait_group.sync.aligned %0;" ::"n"(N) : "memory"); }
__device__ __forceinline__ uint64_t make_desc(uint32_t addr, uint32_t lbo, uint32_t sbo) {
  return (uint64_t)((addr & 0x3FFFF) >> 4) | ((uint64_t)(lbo >> 4) << 16) | ((uint64_t)(sbo >> 4) << 32) | (1ull << 62);
}
__device__ __forceinline__ uint32_t ld_relaxed(const uint32_t* p) {
  uint32_t v; asm volatile("ld.relaxed.gpu.global.u32 %0, [%1];" : "=r"(v) : "l"(p) : "memory"); return v;
}
__device__ __forceinline__ uint32_t ld_acquire(const uint32_t* p) {
  uint32_t v; asm volatile("ld.acquire.gpu.global.u32 %0, [%1];" : "=r"(v) : "l"(p) : "memory"); return v;
}
__device__ __forceinline__ uint4 ld_relaxed4(const uint32_t* p) {
  uint4 v; asm volatile("ld.relaxed.gpu.global.v4.u32 {%0,%1,%2,%3}, [%4];" : "=r"(v.x), "=r"(v.y), "=r"(v.z), "=r"(v.w) : "l"(p) : "memory"); return v;
}
__device__ __forceinline__ uint2 ld_relaxed2(const uint32_t* p) {
  uint2 v; asm volatile("ld.relaxed.gpu.global.v2.u32 {%0,%1}, [%2];" : "=r"(v.x), "=r"(v.y) : "l"(p) : "memory"); return v;
}
__device__ __forceinline__ void st_relaxed(uint32_t* p, uint32_t v) {
  asm volatile("st.relaxed.gpu.global.u32 [%0], %1;" ::"l"(p), "r"(v) : "memory");
}
__device__ __forceinline__ void st_relaxed2(uint32_t* p, uint32_t a, uint32_t b) {
  asm volatile("st.relaxed.gpu.global.v2.u32 [%0], {%1,%2};" ::"l"(p), "r"(a), "r"(b) : "memory");
}
__device__ __forceinline__ void st_relaxed4(uint32_t* p, uint32_t a, uint32_t b, uint32_t c, uint32_t d) {
  asm volatile("st.relaxed.gpu.global.v4.u32 [%0], {%1,%2,%3,%4};" ::"l"(p), "r"(a), "r"(b), "r"(c), "r"(d) : "memory");
}
__device__ __forceinline__ void st_b128(uint32_t* p, uint32_t a, uint32_t b, uint32_t c, uint32_t d) {
  asm volatile("{ .reg .b64 u, v; .reg .b128 w; mov.b64 u, {%1, %2}; mov.b64 v, {%3, %4}; mov.b128 w, {u, v}; st.relaxed.gpu.global.b128 [%0], w; }"
               ::"l"(p), "r"(a), "r"(b), "r"(c), "r"(d) : "memory");
}
__device__ __forceinline__ uint4 ld_b128(const uint32_t* p) {
  uint4 r;
  asm volatile("{ .reg .b64 u, v; .reg .b128 w; ld.relaxed.gpu.global.b128 w, [%4]; mov.b128 {u, v}, w; mov.b64 {%0, %1}, u; mov.b64 {%2, %3}, v; }"
               : "=r"(r.x), "=r"(r.y), "=r"(r.z), "=r"(r.w) : "l"(p) : "memory");
  return r;
}
__device__ __forceinline__ void st_pairs(uint32_t* p, uint32_t a, uint32_t b, uint32_t tag) {
  asm volatile("{ .reg .b64 u, v; mov.b64 u, {%1, %3}; mov.b64 v, {%2, %3}; st.relaxed.gpu.global.v2.b64 [%0], {u, v}; }"
               ::"l"(p), "r"(a), "r"(b), "r"(tag) : "memory");
}
__device__ __forceinline__ uint4 ld_pairs(const uint32_t* p) {
  uint4 v;
  asm volatile("{ .reg .b64 u, v; ld.relaxed.gpu.global.v2.b64 {u, v}, [%4]; mov.b64 {%0, %1}, u; mov.b64 {%2, %3}, v; }"
               : "=r"(v.x), "=r"(v.y), "=r"(v.z), "=r"(v.w) : "l"(p) : "memory");
  return v;
}
__device__ __forceinline__ uint2 ld_pair(const uint32_t* p) {
  uint2 v;
  asm volatile("{ .reg .b64 u; ld.relaxed.gpu.global.b64 u, [%2]; mov.b64 {%0, %1}, u; }" : "=r"(v.x), "=r"(v.y) : "l"(p) : "memory");
  return v;
}
__device__ __forceinline__ void red_release(uint32_t* p, uint32_t v) {
  asm volatile("red.release.gpu.global.add.u32 [%0], %1;" ::"l"(p), "r"(v) : "memory");
}
__device__ __forceinline__ uint32_t ldg_nc1(const void* p) {
  uint32_t v;
  asm volatile("ld.global.nc.u32 %0, [%1];" : "=r"(v) : "l"(p));
  return v;
}
__device__ __forceinline__ uint4 ldg_nc4(const void* p) {
  uint4 v; asm volatile("ld.global.nc.L1::no_allocate.v4.u32 {%0,%1,%2,%3}, [%4];" : "=r"(v.x), "=r"(v.y), "=r"(v.z), "=r"(v.w) : "l"(p)); return v;
}
__device__ __forceinline__ uint4 ldg_stream4(const void* p) {
  uint4 v;
  asm volatile("ld.global.nc.L1::no_allocate.L2::cache_hint.v4.u32 {%0,%1,%2,%3}, [%4], %5;" : "=r"(v.x), "=r"(v.y), "=r"(v.z), "=r"(v.w) : "l"(p), "l"(l2_stream()));
  return v;
}
__device__ __forceinline__ void stg4(void* p, uint4 v) {
  asm volatile("st.global.v4.u32 [%0], {%1,%2,%3,%4};" ::"l"(p), "r"(v.x), "r"(v.y), "r"(v.z), "r"(v.w) : "memory");
}
__device__ __forceinline__ void wait_counter(const uint32_t* p, uint32_t target) {
  uint32_t n = 0;
  while (__any_sync(0xffffffffu, (int)(ld_acquire(p) - target) < 0)) { watchdog(n); }
}
__device__ __forceinline__ uint32_t tagf(float v, uint32_t tag) { return (__float_as_uint(v) & ~3u) | tag; }
__device__ __forceinline__ bool tag_ok(uint4 v, uint32_t tag) { return (((v.x ^ tag) | (v.y ^ tag) | (v.z ^ tag) | (v.w ^ tag)) & 3u) == 0; }
__device__ __forceinline__ float untag_sum(uint32_t a, uint32_t b) { return __uint_as_float(a & ~3u) + __uint_as_float(b & ~3u); }
__device__ __forceinline__ uint4 poll4(const uint32_t* p, uint32_t tag) {
  uint4 v = ld_relaxed4(p);
  uint32_t n = 0;
  while (!__all_sync(0xffffffffu, tag_ok(v, tag))) { v = ld_relaxed4(p); watchdog(n); }
  return v;
}
__device__ __forceinline__ float bf_lo(uint32_t v) { return __uint_as_float(v << 16); }
__device__ __forceinline__ float bf_hi(uint32_t v) { return __uint_as_float(v & 0xffff0000u); }
__device__ __forceinline__ uint32_t pack_bf(float lo, float hi) {
  uint32_t r; asm("cvt.rn.bf16x2.f32 %0, %1, %2;" : "=r"(r) : "f"(hi), "f"(lo)); return r;
}
__device__ __forceinline__ float rbf(float v) { return __uint_as_float(pack_bf(0.f, v) & 0xffff0000u); }
__device__ __forceinline__ uint32_t hmul2(uint32_t a, uint32_t b) {
  uint32_t r; asm("mul.rn.bf16x2 %0, %1, %2;" : "=r"(r) : "r"(a), "r"(b)); return r;
}
__device__ __forceinline__ uint32_t hadd2(uint32_t a, uint32_t b) {
  uint32_t r; asm("add.rn.bf16x2 %0, %1, %2;" : "=r"(r) : "r"(a), "r"(b)); return r;
}
__device__ __forceinline__ uint32_t hsub2(uint32_t a, uint32_t b) {
  uint32_t r; asm("sub.rn.bf16x2 %0, %1, %2;" : "=r"(r) : "r"(a), "r"(b)); return r;
}
__device__ __forceinline__ uint32_t hmax2(uint32_t a, uint32_t b) {
  uint32_t r; asm("max.bf16x2 %0, %1, %2;" : "=r"(r) : "r"(a), "r"(b)); return r;
}
__device__ __forceinline__ float rcp(float x) { float r; asm("rcp.approx.ftz.f32 %0, %1;" : "=f"(r) : "f"(x)); return r; }
__device__ __forceinline__ float ex2(float x) { float r; asm("ex2.approx.ftz.f32 %0, %1;" : "=f"(r) : "f"(x)); return r; }
__device__ __forceinline__ void stmatrix4(uint32_t addr, uint32_t a, uint32_t b, uint32_t c, uint32_t d) {
  asm volatile("stmatrix.sync.aligned.m8n8.x4.shared.b16 [%0], {%1,%2,%3,%4};" ::"r"(addr), "r"(a), "r"(b), "r"(c), "r"(d) : "memory");
}
__device__ __forceinline__ void ldmatrix4(uint32_t addr, uint32_t& a, uint32_t& b, uint32_t& c, uint32_t& d) {
  asm volatile("ldmatrix.sync.aligned.m8n8.x4.shared.b16 {%0,%1,%2,%3}, [%4];" : "=r"(a), "=r"(b), "=r"(c), "=r"(d) : "r"(addr) : "memory");
}
__device__ __forceinline__ void ldmatrix4t(uint32_t addr, uint32_t& a, uint32_t& b, uint32_t& c, uint32_t& d) {
  asm volatile("ldmatrix.sync.aligned.m8n8.x4.trans.shared.b16 {%0,%1,%2,%3}, [%4];" : "=r"(a), "=r"(b), "=r"(c), "=r"(d) : "r"(addr) : "memory");
}
__device__ __forceinline__ void mma16816(float (&d)[4], uint32_t a0, uint32_t a1, uint32_t a2, uint32_t a3, uint32_t b0, uint32_t b1) {
  asm volatile("mma.sync.aligned.m16n8k16.row.col.f32.bf16.bf16.f32 {%0,%1,%2,%3}, {%4,%5,%6,%7}, {%8,%9}, {%0,%1,%2,%3};"
               : "+f"(d[0]), "+f"(d[1]), "+f"(d[2]), "+f"(d[3]) : "r"(a0), "r"(a1), "r"(a2), "r"(a3), "r"(b0), "r"(b1));
}
__device__ __forceinline__ void sts1(uint32_t a, uint32_t v) { asm volatile("st.shared.u32 [%0], %1;" ::"r"(a), "r"(v) : "memory"); }
__device__ __forceinline__ uint4 lds4(uint32_t a) {
  uint4 v; asm volatile("ld.shared.v4.u32 {%0,%1,%2,%3}, [%4];" : "=r"(v.x), "=r"(v.y), "=r"(v.z), "=r"(v.w) : "r"(a) : "memory"); return v;
}
__device__ __forceinline__ uint2 lds2(uint32_t a) {
  uint2 v; asm volatile("ld.shared.v2.u32 {%0,%1}, [%2];" : "=r"(v.x), "=r"(v.y) : "r"(a) : "memory"); return v;
}
__device__ __forceinline__ uint32_t lds1(uint32_t a) {
  uint32_t v; asm volatile("ld.shared.u32 %0, [%1];" : "=r"(v) : "r"(a) : "memory"); return v;
}
__device__ __forceinline__ void sts2(uint32_t a, uint32_t x, uint32_t y) { asm volatile("st.shared.v2.u32 [%0], {%1,%2};" ::"r"(a), "r"(x), "r"(y) : "memory"); }
__device__ __forceinline__ void sts4(uint32_t a, uint4 v) {
  asm volatile("st.shared.v4.u32 [%0], {%1,%2,%3,%4};" ::"r"(a), "r"(v.x), "r"(v.y), "r"(v.z), "r"(v.w) : "memory");
}
__device__ __forceinline__ float silu_f(float v) { return __fdividef(v, 1.f + __expf(-v)); }
__device__ __forceinline__ uint32_t hfma2(uint32_t a, uint32_t b, uint32_t c) {
  uint32_t r; asm("fma.rn.bf16x2 %0, %1, %2, %3;" : "=r"(r) : "r"(a), "r"(b), "r"(c)); return r;
}
__device__ __forceinline__ void split_inv(float sd, uint32_t& ih, uint32_t& il) {
  const float inv = rcp(sd);
  ih = pack_bf(inv, inv);
  const float lo = inv - bf_lo(ih);
  il = pack_bf(lo, lo);
}
__device__ __forceinline__ uint32_t ln_norm(uint32_t x, uint32_t mean2, uint32_t ih, uint32_t il) {
  const uint32_t d = hsub2(x, mean2);
  return hfma2(d, ih, hmul2(d, il));
}
__device__ __forceinline__ uint32_t modul(uint32_t n, uint32_t c1, uint32_t sh) { return hadd2(hmul2(n, c1), sh); }
__device__ __forceinline__ uint32_t ln_mod(uint32_t x, uint32_t mean2, uint32_t ih, uint32_t il, uint32_t c1, uint32_t sh) {
  return modul(ln_norm(x, mean2, ih, il), c1, sh);
}

#define R8(a, i) "+f"(a[i]), "+f"(a[i + 1]), "+f"(a[i + 2]), "+f"(a[i + 3]), "+f"(a[i + 4]), "+f"(a[i + 5]), "+f"(a[i + 6]), "+f"(a[i + 7])
#define D64 "{%0,%1,%2,%3,%4,%5,%6,%7,%8,%9,%10,%11,%12,%13,%14,%15,%16,%17,%18,%19,%20,%21,%22,%23,%24,%25,%26,%27,%28,%29,%30,%31," \
            "%32,%33,%34,%35,%36,%37,%38,%39,%40,%41,%42,%43,%44,%45,%46,%47,%48,%49,%50,%51,%52,%53,%54,%55,%56,%57,%58,%59,%60,%61,%62,%63}"
template <int TB>
__device__ __forceinline__ void mma_ss(float (&d)[64], uint64_t da, uint64_t db, int sc) {
  asm volatile("{\n.reg .pred p;\nsetp.ne.b32 p, %66, 0;\n"
               "wgmma.mma_async.sync.aligned.m64n128k16.f32.bf16.bf16 " D64 ", %64, %65, p, 1, 1, 0, %67;\n}"
               : R8(d, 0), R8(d, 8), R8(d, 16), R8(d, 24), R8(d, 32), R8(d, 40), R8(d, 48), R8(d, 56)
               : "l"(da), "l"(db), "r"(sc), "n"(TB));
}
template <int TB>
__device__ __forceinline__ void mma_rs(float (&d)[64], uint32_t a0, uint32_t a1, uint32_t a2, uint32_t a3, uint64_t db, int sc) {
  asm volatile("{\n.reg .pred p;\nsetp.ne.b32 p, %69, 0;\n"
               "wgmma.mma_async.sync.aligned.m64n128k16.f32.bf16.bf16 " D64 ", {%64,%65,%66,%67}, %68, p, 1, 1, %70;\n}"
               : R8(d, 0), R8(d, 8), R8(d, 16), R8(d, 24), R8(d, 32), R8(d, 40), R8(d, 48), R8(d, 56)
               : "r"(a0), "r"(a1), "r"(a2), "r"(a3), "l"(db), "r"(sc), "n"(TB));
}
#define D128 "{%0,%1,%2,%3,%4,%5,%6,%7,%8,%9,%10,%11,%12,%13,%14,%15,%16,%17,%18,%19,%20,%21,%22,%23,%24,%25,%26,%27,%28,%29,%30,%31," \
             "%32,%33,%34,%35,%36,%37,%38,%39,%40,%41,%42,%43,%44,%45,%46,%47,%48,%49,%50,%51,%52,%53,%54,%55,%56,%57,%58,%59,%60,%61,%62,%63," \
             "%64,%65,%66,%67,%68,%69,%70,%71,%72,%73,%74,%75,%76,%77,%78,%79,%80,%81,%82,%83,%84,%85,%86,%87,%88,%89,%90,%91,%92,%93,%94,%95," \
             "%96,%97,%98,%99,%100,%101,%102,%103,%104,%105,%106,%107,%108,%109,%110,%111,%112,%113,%114,%115,%116,%117,%118,%119,%120,%121,%122,%123,%124,%125,%126,%127}"
#define R128(d, e) R8(d, 0), R8(d, 8), R8(d, 16), R8(d, 24), R8(d, 32), R8(d, 40), R8(d, 48), R8(d, 56), \
                   R8(e, 0), R8(e, 8), R8(e, 16), R8(e, 24), R8(e, 32), R8(e, 40), R8(e, 48), R8(e, 56)
__device__ __forceinline__ void mma256_ss(float (&d)[64], float (&e)[64], uint64_t da, uint64_t db, int sc) {
  asm volatile("{\n.reg .pred p;\nsetp.ne.b32 p, %130, 0;\n"
               "wgmma.mma_async.sync.aligned.m64n256k16.f32.bf16.bf16 " D128 ", %128, %129, p, 1, 1, 0, 1;\n}"
               : R128(d, e) : "l"(da), "l"(db), "r"(sc));
}
__device__ __forceinline__ void mma256_rs(float (&d)[64], float (&e)[64], uint32_t a0, uint32_t a1, uint32_t a2, uint32_t a3, uint64_t db) {
  asm volatile("{\n.reg .pred p;\nsetp.ne.b32 p, 1, 0;\n"
               "wgmma.mma_async.sync.aligned.m64n256k16.f32.bf16.bf16 " D128 ", {%128,%129,%130,%131}, %132, p, 1, 1, 1;\n}"
               : R128(d, e) : "r"(a0), "r"(a1), "r"(a2), "r"(a3), "l"(db));
}
template <int N> __device__ __forceinline__ void keep(float (&a)[N]) {
#pragma unroll
  for (int i = 0; i < N; i++) asm volatile("" : "+f"(a[i])::"memory");
}
template <int N> __device__ __forceinline__ void keep(uint32_t (&a)[N]) {
#pragma unroll
  for (int i = 0; i < N; i++) asm volatile("" : "+r"(a[i])::"memory");
}

#define STAMP(idx) do {} while (0)
#define PROF(grp, cond, idx) do {} while (0)

constexpr float SCL2 = 1.4426950408889634f * 0.08838834764831845f;

__device__ __forceinline__ void pack_p(const float (&s)[64], uint32_t (&p)[32]) {
#pragma unroll
  for (int i = 0; i < 32; i++) p[i] = pack_bf(s[2 * i], s[2 * i + 1]);
}

__device__ __forceinline__ void issue_qk(float (&s)[64], uint32_t q0, uint32_t q1, uint32_t kslot) {
  const uint64_t db = make_desc(kslot, 16, 1024), da0 = make_desc(q0, 16, 1024), da1 = make_desc(q1, 16, 1024);
#pragma unroll
  for (int kk = 0; kk < 8; kk++) mma_ss<0>(s, (kk < 4 ? da0 : da1) + (kk & 3) * 2, db + (kk >> 2) * 1024 + (kk & 3) * 2, kk != 0);
}
__device__ __forceinline__ void issue_pv(float (&o)[64], uint32_t (&p)[32], uint32_t vslot, int acc) {
  uint64_t db = make_desc(vslot, 16384, 1024);
#pragma unroll
  for (int kk = 0; kk < 8; kk++)
    mma_rs<1>(o, p[4 * kk], p[4 * kk + 1], p[4 * kk + 2], p[4 * kk + 3], db + kk * 128, kk == 0 ? acc : 1);
}

template <int H>
__device__ __forceinline__ void store_chunk(const float (&a)[64], uint32_t addr) {
#pragma unroll
  for (int i = 8 * H; i < 8 * H + 8; i += 2)
    stmatrix4(addr ^ ((i & 7) << 4), pack_bf(a[4 * i], a[4 * i + 1]), pack_bf(a[4 * i + 2], a[4 * i + 3]),
              pack_bf(a[4 * i + 4], a[4 * i + 5]), pack_bf(a[4 * i + 6], a[4 * i + 7]));
}
template <int H>
__device__ __forceinline__ void store_chunk(const float (&a)[64], float i0, float i1, uint32_t addr) {
#pragma unroll
  for (int i = 8 * H; i < 8 * H + 8; i += 2)
    stmatrix4(addr ^ ((i & 7) << 4), pack_bf(a[4 * i] * i0, a[4 * i + 1] * i0), pack_bf(a[4 * i + 2] * i1, a[4 * i + 3] * i1),
              pack_bf(a[4 * i + 4] * i0, a[4 * i + 5] * i0), pack_bf(a[4 * i + 6] * i1, a[4 * i + 7] * i1));
}
__device__ __forceinline__ float inv_quad_sum(float l) {
  l += __shfl_xor_sync(0xffffffffu, l, 1);
  l += __shfl_xor_sync(0xffffffffu, l, 2);
  return rcp(l);
}

__device__ __forceinline__ void write_table(uint32_t table, bool ca, uint32_t t, const uint4& m0, const uint4& m1) {
  float c0 = untag_sum(m0.x, m1.x), c1 = untag_sum(m0.y, m1.y), c2 = untag_sum(m0.z, m1.z), c3 = untag_sum(m0.w, m1.w);
  if (ca) { c0 = 1.f + rbf(c0); c1 = 1.f + rbf(c1); c2 = 1.f + rbf(c2); c3 = 1.f + rbf(c3); }
  const uint32_t d = table + (t >> 2) * 64 + (t & 1) * 32 + (t & 2) * 2 + (ca ? 0 : 8);
  sts1(d, pack_bf(c0, c1));
  sts1(d + 16, pack_bf(c2, c3));
}

__device__ __forceinline__ void ln_scalars(float mean, float var, float& mb, float& sd) {
  mb = rbf(mean);
  float r; asm("sqrt.approx.ftz.f32 %0, %1;" : "=f"(r) : "f"(rbf(rbf(var) + 1e-5f)));
  sd = rbf(r);
}

__global__ void __cluster_dims__(2, 1, 1) __launch_bounds__(384, 1) fused_kernel(const __grid_constant__ Maps maps, const Ptrs P) {
  extern __shared__ __align__(1024) uint8_t smem_raw[];
  const uint32_t base = smem_u32(smem_raw);
  const int tid = threadIdx.x, lane = tid & 31;
  const int warp = __shfl_sync(0xffffffffu, tid >> 5, 0);
  const int b = blockIdx.x;
  PROF(31, tid == 0, 0);

  if (b >= NMAIN) {
    float* sc = reinterpret_cast<float*>(smem_raw);
    float* red = sc + DM;
    for (int k = tid; k < DM; k += 384) sc[k] = rbf(silu_f(__bfloat162float(P.c[k])));
    __syncthreads();
    if (tid < 256) {
      const int col = 2048 + (b - NMAIN) * 1024 + (tid & 127) * 8, r0 = (tid >> 7) * 512;
      float acc[8];
#pragma unroll
      for (int e = 0; e < 8; e++) acc[e] = 0.f;
#pragma unroll 1
      for (int r = r0; r < r0 + 512; r += HU) {
        uint4 w[HU];
#pragma unroll
        for (int u = 0; u < HU; u++) w[u] = ldg_stream4(P.w_mod + (size_t)(r + u) * NMOD + col);
#pragma unroll
        for (int u = 0; u < HU; u++) {
          float s = sc[r + u];
          acc[0] += s * bf_lo(w[u].x); acc[1] += s * bf_hi(w[u].x); acc[2] += s * bf_lo(w[u].y); acc[3] += s * bf_hi(w[u].y);
          acc[4] += s * bf_lo(w[u].z); acc[5] += s * bf_hi(w[u].z); acc[6] += s * bf_lo(w[u].w); acc[7] += s * bf_hi(w[u].w);
        }
      }
      if (tid >= 128) {
#pragma unroll
        for (int e = 0; e < 8; e++) red[(tid & 127) * 8 + e] = acc[e];
      }
      const uint32_t tag = ld_relaxed(&g_epoch) % 3 + 1;
      bar_sync(1, 256);
      if (tid < 128) {
        uint32_t o[8];
#pragma unroll
        for (int e = 0; e < 8; e++) o[e] = __float_as_uint(rbf(acc[e] + red[tid * 8 + e])) | tag;
        st_relaxed4(g_mod + col, o[0], o[1], o[2], o[3]);
        st_relaxed4(g_mod + col + 4, o[4], o[5], o[6], o[7]);
        const uint4 wr = ldg_nc4(P.w_r + tid * 8);
        const uint32_t wv[4] = {wr.x, wr.y, wr.z, wr.w};
        float dsum = 0.f;
#pragma unroll
        for (int e = 0; e < 8; e++) {
          const float m = bf_hi(o[e]);
          dsum += (b == NMAIN + 2 ? rbf(1.f + m) : m) * ((e & 1) ? bf_hi(wv[e >> 1]) : bf_lo(wv[e >> 1]));
        }
#pragma unroll
        for (int k = 16; k > 0; k >>= 1) dsum += __shfl_xor_sync(0xffffffffu, dsum, k);
        if (lane == 0) st_relaxed(g_mod + (b - NMAIN) * 4 + warp, tagf(dsum, tag));
      }
    }
    PROF(2, tid == 0, 1);
    return;
  }

  const int rank = b & 1;
  const int rb = ((b >> 4) << 1) | rank, cj = (b >> 1) & 7;
  const bool late = b & 4;
  const uint32_t bfull = base + OFF_BAR, bempty = bfull + NSLOT * 8;
  const uint32_t gfull = bempty + NSLOT * 8, gempty = gfull + 32;
  const uint32_t bar_ofull = gempty + 32;
  const uint32_t bar_ofree = bar_ofull + 32;
  const uint32_t bar_par = bar_ofree + 32;
  const uint32_t bar_mod = bar_par + 8;
  const uint32_t bar_pread = bar_mod + 8;
  const uint32_t bar_xres = bar_pread + 8;
  const uint32_t bar_ring = bar_xres + 8;
  const uint32_t bar_box = bar_ring + 24;
  const uint32_t bar_go = bar_box + 96;
  const uint32_t bar_go2 = bar_go + 16;
  const uint32_t bar_cnt = bar_go + 24;
  const uint32_t xfull = bar_go + 40, xempty = xfull + 32;
  const uint32_t bar_hw = xempty + 32, bar_hx = bar_hw + 8;
  const uint32_t bar_hpub = bar_hx + 16;
  const uint32_t bar_win = bar_hpub + 16;
  const uint32_t bar_rx = bar_win + 8;
  const uint32_t bar_sel = bar_rx + 8;
  const uint32_t bar_gate = bar_sel + 8;
  const uint32_t bar_rel = bar_gate + 8;
  const uint32_t bar_od = bar_rel + 8;
  const uint32_t bar_mod2 = bar_od + 8;
  const uint32_t bar_res = bar_go + 8;
  const uint32_t stage = base + OFF_STAGE, par = base + OFF_PAR;

  if (warp == 10 && elect_one()) prefetch_map(&maps.wm);
  if (warp == 8 && elect_one()) {
    for (int s = 0; s < NSLOT; s++) { mbar_init(bfull + s * 8, 1); mbar_init(bempty + s * 8, 16); }
    for (int s = 0; s < 4; s++) { mbar_init(gfull + s * 8, 1); mbar_init(gempty + s * 8, 16); mbar_init(xfull + s * 8, 1); mbar_init(xempty + s * 8, 8); mbar_init(bar_ofree + s * 8, 1); mbar_init(bar_ofull + s * 8, 128); }
    mbar_init(bar_par, 64); mbar_init(bar_mod, 256); mbar_init(bar_pread, 2); mbar_init(bar_xres, 1);
    mbar_init(bar_ring, 8); mbar_init(bar_ring + 8, 8); mbar_init(bar_ring + 16, 8);
    mbar_init(bar_go, 1); mbar_init(bar_go2, 1); mbar_init(bar_cnt, 1); mbar_init(bar_cnt + 8, 1); mbar_init(bar_hpub, 8); mbar_init(bar_hpub + 8, 8); mbar_init(bar_res, 1); mbar_init(bar_win, 1); mbar_init(bar_rx, 1); mbar_init(bar_sel, 64); mbar_init(bar_gate, 8); mbar_init(bar_rel, 8); mbar_init(bar_od, 1); mbar_init(bar_mod2, 64);
    for (int s = 0; s < 12; s++) mbar_init(bar_box + s * 8, 1);
    asm volatile("fence.mbarrier_init.release.cluster;" ::: "memory");
    prefetch_map(&maps.x); prefetch_map(&maps.wq); prefetch_map(&maps.k); prefetch_map(&maps.v);
  }
  if (warp == 9 && elect_one()) {
    mbar_init(bar_hw, 1); mbar_init(bar_hx, 1); mbar_init(bar_hx + 8, 1);
    asm volatile("fence.mbarrier_init.release.cluster;" ::: "memory");
    mbar_expect_tx(bar_hw, 32768);
    mbar_expect_tx(bar_hx, 16384);
    mbar_expect_tx(bar_hx + 8, 16384);
    const __nv_bfloat16* xs = P.x + (size_t)(rb * 128 + cj * 16) * DM;
    bulk_load(base + 2 * GST_BYTES, xs, 16384, bar_hx);
    if (!late) {
      tma2d(stage, &maps.wm, (b >> 1) * 32, rank * 512, bar_hw);
      tma2d(stage + 16384, &maps.wm, (b >> 1) * 32, rank * 512 + 256, bar_hw);
    }
    bulk_load(base + 3 * GST_BYTES, xs + 8 * DM, 16384, bar_hx + 8);
  }
  cluster_arrive();

  if (warp >= 8) {
    asm volatile("setmaxnreg.dec.sync.aligned.u32 40;");
    if (warp < 10) bar_arrive(1, 320);
    const uint32_t epoch = ld_relaxed(&g_epoch);
    cluster_wait();
    if (warp == 8) {
      const int kvrow = (cj >> 1) * SK + (SK - WIN);
      int wch = cj * 8 + rank * 2;
#pragma unroll 1
      for (int ps = 0; ps < 3; ps++) {
        const CUtensorMap* mw = ps == 2 ? &maps.wo : &maps.wq;
        const uint32_t xt = ps == 1 ? XT1 : XT2, wt = ps == 0 ? WT0 : (ps == 1 ? WT1 : WT2);
        const int nst = ps == 2 ? 32 : 16;
#pragma unroll 1
        for (int i = 0; i < nst; i++) {
          const uint32_t bf = gfull + (i & 3) * 8;
          const int kt = ps == 2 ? (((cj & 1) * 4 + ((i >> 1) & 3)) * 4 + (i >> 3)) * 2 + (i & 1) : (ps ? i : slice_of(i) + (b & 14)) & 15;
          const uint32_t wd = base + unit_of(wt, i & 3) + rank * UNIT, xd = base + unit_of(xt, i & 3);
          const uint8_t* xs = g_act + (uint32_t)(rb * 80 + (ps - 1) * 16 + kt) * UNIT;
          if (ps == 0 && i == HD) mbar_wait(bar_mod, 0);
          const bool xfirst = ps && i < 2;
          if (ps == 2 && i == 0) mbar_wait(bar_ofree + 24, 0);
          if (i == 0) fence_async();
          mbar_wait(gempty + (i & 3) * 8, ((i >> 2) & 1) ^ 1);
          if (elect_one()) {
            mbar_expect_tx(bf, ps ? GST_BYTES : 2 * UNIT);
            if (xfirst) bulk_load_stream(xd, xs, UNIT, bf);
          }
          if (ps && i < 4) mbar_wait(bempty + i * 8, 1);
          if (elect_one()) tma3d_mc<true>(wd, mw, 0, (i == 31 ? kt ^ (rank * 32) : kt) * 64, i == 31 ? cj * 2 : wch, bf);
          if (ps) {
            if (i == 16 || i == 24) { mbar_wait(bar_cnt + i - 16, 0); fence_async(); }
            if (i == RES0) mbar_wait(bar_res, 0);
            if (i == 2) mbar_wait(bar_ofree + (ps - 1) * 16, 0);
            if (elect_one()) {
              if (i == 31) bulk_load(xd, xs, UNIT, bf); else if (!xfirst) bulk_load_stream(xd, xs, UNIT, bf);
              mbar_arrive_pred(bar_go, i == GOST - 1);
              if (PG0 < 16) mbar_arrive_pred(bar_go2, ps == 1 && i == PG0);
              mbar_arrive_pred(bar_od, i == (ps == 1 ? ODS1 : ODS));
              if (i == RES0) mbar_expect_tx(bar_xres, 32768);
              if (i == RES0 || i == RES1) tma2d(base + OFF_RES + (i == RES1) * UNIT, &maps.x, cj * 128 + (i == RES1) * 64, rb * 128, bar_xres);
            }
          }
        }
        if (ps == 2) break;
        wch = ps ? ((wch >> 3) ^ rank) * 2 : wch + 4;
#pragma unroll 1
        for (int u = 0; u < 16; u++) {
          const bool isk = (u == 0) || ((u & 1) && u < 15);
          const int blk = (isk ? (u + 1) >> 1 : (u == 15 ? 7 : (u >> 1) - 1)) & 3;
          const uint32_t sl = base + unit_of(ps ? AT1 : AT0, u & 3) + rank * UNIT, bf = bfull + (u & 3) * 8;
          if (u < 4) mbar_wait(gempty + ((u + 1) >> 1) * 8, 1);
          mbar_wait(bempty + (u & 3) * 8, ((u >> 2) & 1) ^ 1);
          if (elect_one()) {
            mbar_arrive_pred(bar_go2, ps && u + 16 == PG0);
            mbar_expect_tx(bf, SLOT_BYTES);
            tma3d_mc<false>(sl, isk ? &maps.k : &maps.v, 0, kvrow + blk * 128, rank, bf);
          }
        }
      }
      if (elect_one()) mbar_expect_tx(bar_rx, UNIT);
      mbar_wait(bar_rel, 0);
      if (elect_one()) {
        bulk_load_stream(base + UNIT, g_act + (uint32_t)(rb * 80 + 16 + 63 - (cj & 1) * 32) * UNIT, UNIT, bar_rx);
      }
      if (b < NFFN) {
#pragma unroll 1
        for (int u = 0; u < 12; u++) {
          const uint32_t dst = base + unit_of(u < 4 ? FT_G : (u < 8 ? FT_U : FT_D), u & 3);
          if (elect_one()) mbar_expect_tx(bar_box + u * 8, UNIT);
          if (u == FB0 || u == FB1 || u == FB2) mbar_wait(bar_ring + (u == FB2 ? 16 : u == FB1 ? 8 : 0), 0);
          const int fp = u < FPB ? FPACE0 : FPACE;
          if (u >= fp) mbar_wait(bar_box + (u - fp) * 8, 0);
          if (elect_one()) {
            if (u < 8) tma2d(dst, u < 4 ? &maps.wg : &maps.wu, b * 32, (u & 3) * 256, bar_box + u * 8);
            else tma3d(dst, &maps.wd, 0, b * 32, (u - 8) * 4, bar_box + u * 8);
          }
        }
      }
    } else if (warp == 9) {
      const uint32_t target = 8 * (epoch + 1);
      uint32_t hmask = 0;
#pragma unroll 1
      for (int i = 0; i < 16; i++) {
        if (i == HDX) mbar_wait(bar_mod, 0);
        const int kt = (2 * cj + slice_of(i)) & 15;
        const uint32_t need = i == 15 ? 0xffffu : 1u << kt;
        if (i >= NRS && (hmask & need) != need) {
          uint32_t n = 0;
          do { hmask = __ballot_sync(0xffffffffu, ld_acquire(&g_cnt_h[rb * 32 + (lane & 15)]) == epoch + 1); watchdog(n); } while ((hmask & need) != need);
          PROF(1, lane == 0 && i == NRS, 26);
          fence_async();
        }
        mbar_wait(xempty + (i & 3) * 8, ((i >> 2) & 1) ^ 1);
        if (elect_one()) {
          mbar_expect_tx(xfull + (i & 3) * 8, UNIT);
          if (i < NRS) tma2d(base + (i & 3) * GST_BYTES, &maps.x, kt * 64, rb * 128, xfull + (i & 3) * 8);
          else bulk_load_stream(base + (i & 3) * GST_BYTES, g_act + (uint32_t)(rb * 80 + kt) * UNIT, UNIT, xfull + (i & 3) * 8);
        }
      }
      prefetch_map(&maps.wo);
#pragma unroll 1
      for (int t = 0; t < 4; t++) {
        if (t & 1) mbar_wait(bar_od, t >> 1);
#pragma unroll 1
        for (int p = 0; p < 32768 / OPS; p++) {
          const uint32_t w = p / (16384 / OPS), c = (p / (8192 / OPS)) & 1, off = w * 8192 + (p % (8192 / OPS)) * OPS;
          mbar_wait(bar_ofull + (t & 1) * 16 + w * 8, t >> 1);
          if (elect_one()) {
            bulk_store(g_act + (uint32_t)(rb * 80 + 16 + (cj * 4 + t) * 2 + c) * UNIT + off, base + unit_of(QT, 2 * t + c) + off, OPS);
            asm volatile("cp.async.bulk.commit_group;" ::: "memory");
            asm volatile("cp.async.bulk.wait_group.read %0;" ::"n"(OFL) : "memory");
          }
        }
        if (elect_one()) {
          asm volatile("cp.async.bulk.wait_group.read 0;" ::: "memory");
          mbar_arrive(t < 3 ? bar_ofree + t * 8 : bar_res);
          asm volatile("cp.async.bulk.wait_group 0;" ::: "memory");
          fence_async();
          red_release(&g_cnt_o[((rb * 4 + t) * 2 + (cj >> 2)) * 32], 2);
        }
        if (t) {
          wait_counter(&g_cnt_o[(rb * 8 + 2 * t + (cj & 1)) * 32], target);
          if (t & 1) wait_counter(&g_cnt_o[(rb * 8 + (t == 1 ? cj & 1 : 7 - (cj & 1))) * 32], target);
          if (elect_one()) mbar_arrive(t == 1 ? bar_ofree + 24 : bar_cnt + t * 8 - 16);
        }
      }
      PROF(2, lane == 0, 27);
      const uint32_t tag = epoch % 3 + 1;
      const uint32_t* inbox = g_cand + (b >> 1) % CR * 512 + (lane & 15) * CS;
      mbar_wait(bar_ring + 16, 0);
      uint32_t c0 = ld_relaxed(inbox), n = 0;
#define CAND_STEP(cv)                                                                                        \
      {                                                                                                      \
        const bool valid = (cv & 3u) == tag, all = __all_sync(0xffffffffu, valid);                           \
        const uint32_t best = __reduce_max_sync(0xffffffffu, valid ? cv : 0u);                               \
        const uint32_t blk = __ffs(__ballot_sync(0xffffffffu, cv == best)) - 1;                              \
        if (best) sts2(par + PAR_CONST + 56, best, (blk << 7 | (~best >> 2 & 127)) | (all ? 0x1800 : 0x800)); \
        if (all) break;                                                                                      \
        cv = ld_relaxed(inbox);                                                                              \
      }
      while (true) { CAND_STEP(c0) watchdog(n); }
    } else {
      const int t2 = tid - 320;
      if (late && warp == 10) {
        mbar_wait(bar_hx, 0);
        if (elect_one()) {
          tma2d(stage, &maps.wm, (b >> 1) * 32, rank * 512, bar_hw);
          tma2d(stage + 16384, &maps.wm, (b >> 1) * 32, rank * 512 + 256, bar_hw);
        }
      }
      {
        const uint32_t tag = epoch % 3 + 1;
        mbar_wait(bar_hx + 8, 0);
        mbar_wait(bar_hw, 0);
        __nanosleep(late ? OSL2 : OSL);
        {
          const uint32_t t7 = (warp & 1) * 64 + (lane >> 4) * 32 + 16 + (lane & 15);
          const uint32_t* pm = g_modp + ((cj * 128 + t7 * 4) & (DM - 1));
          uint4 m0, m1, m2, m3;
          uint32_t n = 0;
          do {
            m0 = ld_relaxed4(pm); m1 = ld_relaxed4(pm + 2 * DM); m2 = ld_relaxed4(pm + DM); m3 = ld_relaxed4(pm + 3 * DM);
            watchdog(n);
          } while (!__all_sync(0xffffffffu, tag_ok(m0, tag) && tag_ok(m1, tag) && tag_ok(m2, tag) && tag_ok(m3, tag)));
          write_table(par, false, t7, m0, m1);
          write_table(par, true, t7, m2, m3);
          mbar_arrive(bar_mod2);
        }
      }
      mbar_wait(bar_hpub + (warp & 1) * 8, 0);
      PROF(1, t2 == 0, 24);
#pragma unroll 1
      for (int c = 0; c < 8; c++) {
        const uint32_t off = (warp & 1) * UNIT + c * 2048 + lane * 16;
        uint8_t* dst = g_act + (uint32_t)(rb * 80 + cj * 2) * UNIT + off;
        const uint4 v0 = lds4(stage + off), v1 = lds4(stage + off + 512), v2 = lds4(stage + off + 1024), v3 = lds4(stage + off + 1536);
        stg4(dst, v0); stg4(dst + 512, v1); stg4(dst + 1024, v2); stg4(dst + 1536, v3);
      }
      __syncwarp();
      PROF(1, t2 == 0, 15);
      if (lane == 0) {
        mbar_arrive(bar_pread);
        red_release(&g_cnt_h[rb * 32 + cj * 2 + (warp & 1)], 1);
        PROF(1, t2 == 0, 25);
        prefetch_map(&maps.wg); prefetch_map(&maps.wu); prefetch_map(&maps.wd); prefetch_map(&maps.out);
      }
      __syncwarp();
      if (b < NFFN) {
        mbar_wait(bar_go2, 0);
        const __nv_bfloat16* pg = ((b & 1) ? P.w_up : P.w_gate) + (b >> 1) * 64 + (size_t)t2 * FF;
        const __nv_bfloat16* pd = P.w_down + (size_t)b * 32768 + t2 * 64;
        PROF(2, t2 == 0, 13);
#pragma unroll 1
        for (int i = 0; i < WN; i += WB) {
          uint32_t v[WB];
#pragma unroll
          for (int u = 0; u < WB; u++) {
            const int k = i + u;
            asm volatile("ld.global.cg.L2::128B.u32 %0, [%1];" : "=r"(v[u]) : "l"(k < 16 ? pg + (size_t)k * 64 * FF : pd + (k - 16) * 4096));
          }
#pragma unroll
          for (int u = 1; u < WB; u++) v[0] ^= v[u];
          sts1(par + PAR_SINK + t2 * 4, v[0]);
        }
        PROF(2, t2 == 0, 14);
      }
      const uint32_t tag = epoch % 3 + 1;
      mbar_wait(bar_go, 0);
      bar_sync(4, 64);
      if (warp == 10) {
        const uint32_t* src = g_mod + 2 * DM + cj * 128 + lane * 4;
        const uint2 wr = *reinterpret_cast<const uint2*>(P.w_r + cj * 128 + lane * 4);
        uint4 vga, vsb, vcb, vgb;
        uint32_t n = 0;
        do {
          vga = ld_relaxed4(src); vsb = ld_relaxed4(src + DM); vcb = ld_relaxed4(src + 2 * DM); vgb = ld_relaxed4(src + 3 * DM);
          watchdog(n);
        } while (!__all_sync(0xffffffffu, tag_ok(vga, tag) && tag_ok(vsb, tag) && tag_ok(vcb, tag) && tag_ok(vgb, tag)));
        const float c0 = rbf(1.f + bf_hi(vcb.x)), c1 = rbf(1.f + bf_hi(vcb.y)), c2 = rbf(1.f + bf_hi(vcb.z)), c3 = rbf(1.f + bf_hi(vcb.w));
        const float a0 = c0 * bf_lo(wr.x), a1 = c1 * bf_hi(wr.x), a2 = c2 * bf_lo(wr.y), a3 = c3 * bf_hi(wr.y);
        const uint32_t h0 = pack_bf(a0, a1), h1 = pack_bf(a2, a3);
        const uint32_t t1 = par + PAR_T1 + (lane >> 2) * 64 + (lane & 1) * 32 + (lane & 2) * 2;
        sts1(t1, h0); sts1(t1 + 8, pack_bf(a0 - bf_lo(h0), a1 - bf_hi(h0)));
        sts1(t1 + 16, h1); sts1(t1 + 24, pack_bf(a2 - bf_lo(h1), a3 - bf_hi(h1)));
        const uint32_t tg = par + PAR_SINK + (lane >> 3) * 64 + (lane & 1) * 32 + (lane & 6) * 2;
        sts1(tg, __byte_perm(vga.x, vga.y, 0x7632)); sts1(tg + 16, __byte_perm(vga.z, vga.w, 0x7632));
        sts4(par + PAR_T2 + lane * 32, make_uint4(pack_bf(c0, c1), __byte_perm(vsb.x, vsb.y, 0x7632), __byte_perm(vgb.x, vgb.y, 0x7632), __byte_perm(vga.x, vga.y, 0x7632)));
        sts4(par + PAR_T2 + lane * 32 + 16, make_uint4(pack_bf(c2, c3), __byte_perm(vsb.z, vsb.w, 0x7632), __byte_perm(vgb.z, vgb.w, 0x7632), __byte_perm(vga.z, vga.w, 0x7632)));
      } else {
        const uint4 g = poll4((lane & 8) ? g_mod + 8 - (lane & 1) * 4 : g_mod + 5 * DM + (b >> 4) * 128 + (lane & 7) * 16 + (b & 12), tag);
        sts1(par + PAR_CONST + 60, 0);
        if (lane < 8) sts1(par + PAR_CONST + 16 + lane * 4, (b & 2) ? ((b & 1) ? g.w : g.z) : ((b & 1) ? g.y : g.x));
        else if (lane < 10) sts2(par + PAR_CONST + (lane - 8) * 8, __float_as_uint(untag_sum(g.x, g.y) + untag_sum(g.z, g.w)), epoch);
      }
      __syncwarp();
#pragma unroll 4
      for (int q = 0; q < 32; q++) st_b128(g_xch + ((size_t)b * 8 * 256 + q * 64 + t2) * 4, (epoch & 1) << 16, 0, 0, 0);
      for (int q = 0; q < 2; q++) st_relaxed4(g_stats + ((size_t)cj * SEQ + rb * 128 + q * 64 + t2) * 4, 0, 0, 0, 0);
      if (b < NFFN)
        for (int q = 0; q < 2; q++) st_relaxed4(ypart_slot(b, q * 64 + t2), 0, 0, 0, 0);
      st_relaxed4(g_row + rb * 2 * DM + (t2 >> 5) * DM + cj * 128 + (t2 & 31) * 4, 0, 0, 0, 0);
      __threadfence();
      mbar_arrive(bar_par);
      mbar_wait(bar_gate, 0);
      uint32_t have = 0, n = 0;
      while (true) {
        const uint32_t st = lds1(par + PAR_CONST + 60) >> 7;
        if ((st & 31) != have) {
          const uint32_t* hsrc = g_row + (st & 15) * 2 * DM + t2 * 4;
          uint4 hv[4];
          bool ok = true;
#pragma unroll
          for (int i = 0; i < 4; i++) hv[i] = ld_pairs(hsrc + i * 256);
#pragma unroll
          for (int i = 0; i < 4; i++) {
            sts2(base + ((FT_G >> i * 4) & 15) * UNIT + (warp & 1) * 8192 + 256 + lane * 8, hv[i].x, hv[i].z);
            ok = ok && hv[i].y == tag && hv[i].w == tag;
          }
          have = __all_sync(0xffffffffu, ok) ? st & 31 : 0;
        }
        if ((st ^ have) == 32) break;
        watchdog(n);
      }
      mbar_arrive(bar_sel);
    }
    __syncwarp();
    cluster_arrive();
    {
      const uint32_t tag = epoch % 3 + 1, t3 = tid - 256;
      mbar_wait(bar_win, 0);
      uint2 win = lds2(par + PAR_CONST + 56);
      win.y &= 0x7ff;
      const uint32_t* fsrc = g_row + (win.y >> 7) * 2 * DM + (b >> 4) * 128 + (t3 & 7) * 16 + (b & 6) * 2 + ((b >> 2) & 2);
      const uint32_t* ysrc = ypart_slot(min(t3, NFFN - 1), b);
      uint2 fh = ld_pair(fsrc), fx = ld_pair(fsrc + DM);
      uint4 ya = ld_b128(ysrc);
      const float rwin = __uint_as_float(((int)win.x < 0 ? win.x & 0x7fffffffu : ~win.x) & ~0x1ffu);
      const float rs = rbf(rcp(1.f + __expf(-rbf(rwin))));
      uint32_t n = 0;
      while (__any_sync(0xffffffffu, fh.y != tag || fx.y != tag)) { fh = ld_pair(fsrc); fx = ld_pair(fsrc + DM); watchdog(n); }
      while (true) {
        const bool miss = ((ya.x & 1) | (ya.y & 1) << 1) != tag;
        if (!__any_sync(0xffffffffu, miss)) break;
        if (miss) ya = ld_b128(ysrc);
        watchdog(n);
      }
      PROF(8, t3 == 0, 5);
      float y[8] = {bf_lo(ya.x & ~1u), bf_hi(ya.x), bf_lo(ya.y & ~1u), bf_hi(ya.y), bf_lo(ya.z), bf_hi(ya.z), bf_lo(ya.w), bf_hi(ya.w)};
#pragma unroll
      for (int h = 4; h > 0; h >>= 1) {
        const bool up = lane & (h * 2);
#pragma unroll
        for (int e = 0; e < h; e++) y[e] = (up ? y[e + h] : y[e]) + __shfl_xor_sync(0xffffffffu, up ? y[e] : y[e + h], h * 2);
      }
      y[0] += __shfl_xor_sync(0xffffffffu, y[0], 1);
      if (!(lane & 1)) sts1(par + PAR_RED + 64 + t3 * 2, __float_as_uint(y[0]));
      bar_sync(4, 128);
      if (t3 < 8) {
        float y0 = 0.f;
#pragma unroll
        for (int w7 = 0; w7 < 7; w7++) y0 += __uint_as_float(lds1(par + PAR_RED + 64 + w7 * 32 + t3 * 4));
        const uint32_t gv = lds1(par + PAR_CONST + 16 + t3 * 4);
        const uint32_t upd = hmul2(pack_bf(y0, y0), pack_bf(rs, rs));
        const uint32_t r = hadd2(fx.x, hmul2(__byte_perm(gv, gv, 0x3232), hadd2(fh.x, upd)));
        reinterpret_cast<uint16_t*>(P.out)[(size_t)win.y * DM + (b >> 4) * 128 + t3 * 16 + (b & 15)] = (b & 1) ? r >> 16 : r;
        if (b == 0 && t3 == 0) st_relaxed(&g_epoch, epoch + 1);
      }
      PROF(31, t3 == 0, 36);
    }
    cluster_wait();
  } else {
    const int wg = warp >> 2;

    uint32_t tag;
    {
      uint32_t* const pmod = g_modp + rank * 2 * DM + (b >> 1) * 32 + lane;
      uint32_t* const pln = g_ln1 + (rb * 128 + cj * 16 + warp) * 4;
      uint32_t sc[8];
#pragma unroll
      for (int k = 0; k < 8; k++) sc[k] = ldg_nc1(P.c + rank * 512 + warp * 64 + k * 8 + (lane & 3) * 2);
      const uint32_t epoch = ld_relaxed(&g_epoch);
      if (warp == 0) st_relaxed(pmod, 0);
      if (lane == 0) { st_b128(pln, 0, 0, 0, 0); st_b128(pln + 32, 0, 0, 0, 0); }
      asm volatile("setmaxnreg.inc.sync.aligned.u32 232;");
      bar_sync(1, 320);
#pragma unroll
      for (int k = 0; k < 8; k++) sc[k] = pack_bf(silu_f(bf_lo(sc[k])), silu_f(bf_hi(sc[k])));
      keep(sc);
      tag = epoch % 3 + 1;
#pragma unroll
      for (int part = 0; part < 4; part++) {
        if (!(part & 1)) {
          const uint32_t xa = base + (2 + part / 2) * GST_BYTES + warp * 2048 + lane * 16;
          mbar_wait(bar_hx + part * 4, 0);
          float s0 = 0.f, s1 = 0.f, q0 = 0.f, q1 = 0.f;
#pragma unroll
          for (int q = 0; q < 4; q++) {
            const uint4 xv = lds4(xa + q * 512);
            const uint32_t u[4] = {xv.x, xv.y, xv.z, xv.w};
#pragma unroll
            for (int e = 0; e < 4; e++) { const float lo = bf_lo(u[e]), hi = bf_hi(u[e]); s0 += lo; s1 += hi; q0 += lo * lo; q1 += hi * hi; }
          }
          s0 += s1; q0 += q1;
#pragma unroll
          for (int o = 16; o > 0; o >>= 1) { s0 += __shfl_xor_sync(0xffffffffu, s0, o); q0 += __shfl_xor_sync(0xffffffffu, q0, o); }
          const float mean = s0 * (1.f / DM);
          float mb, sd;
          ln_scalars(mean, fmaxf(q0 * (1.f / DM) - mean * mean, 0.f), mb, sd);
          uint32_t ih, il;
          split_inv(sd, ih, il);
          if (lane == 0) st_b128(pln + part * 16, pack_bf(mb, mb), ih, il, tag);
          PROF(1, tid == 0 && part == 2, 4);
        } else if (late == (part == 3)) {
          const uint32_t fr = (lane & 7) + (lane >> 4) * 8, tq = lane & 3;
          const uint32_t wa = stage + warp * 4096 + fr * 64 + ((((lane >> 3) & 1) ^ ((fr >> 1) & 3)) << 4);
          float d0[4] = {0.f, 0.f, 0.f, 0.f}, d1[4] = {0.f, 0.f, 0.f, 0.f};
          mbar_wait(bar_hw, 0);
#pragma unroll
          for (int ks = 0; ks < 4; ks++) {
            uint32_t w[8];
            ldmatrix4t(wa + ks * 1024, w[0], w[1], w[2], w[3]);
            ldmatrix4t((wa ^ 32) + ks * 1024, w[4], w[5], w[6], w[7]);
            mma16816(d0, w[0], w[1], w[2], w[3], sc[2 * ks], sc[2 * ks + 1]);
            mma16816(d1, w[4], w[5], w[6], w[7], sc[2 * ks], sc[2 * ks + 1]);
          }
          sts1(base + 2 * GST_BYTES + warp * 2048 + (tq * 8 + (lane >> 2)) * 4, __float_as_uint((tq & 2) ? ((tq & 1) ? d1[2] : d1[0]) : ((tq & 1) ? d0[2] : d0[0])));
          bar_sync(1, 256);
          if (warp == 0) {
            float s = 0.f;
#pragma unroll
            for (int w8 = 0; w8 < 8; w8++) s += __uint_as_float(lds1(base + 2 * GST_BYTES + w8 * 2048 + lane * 4));
            st_relaxed(pmod, (__float_as_uint(s) & ~3u) | tag);
          }
          PROF(1, tid == 0, 3);
        }
      }
      cluster_wait();
      if (wg == 1) bar_arrive(2, 256);
    }

    float f0 = 0.f, f1 = 0.f;
    const uint32_t rempty = lane < 2 ? mapa(bempty, lane & 1) : 0;
    constexpr uint32_t GE = NSLOT * 8 + 32;
    float o[64], s[64];
#pragma unroll 1
    for (int ps = 0; ps < 3; ps++) {
      {
        const uint32_t xt = ps == 1 ? XT1 : XT2, wt = ps == 1 ? WT1 : WT2;
        const int nst = ps == 2 ? 28 : 14;
        if (ps == 0) {
          float ga[64], gb[64];
#pragma unroll
          for (int i = 0; i < 64; i++) { ga[i] = 0.f; gb[i] = 0.f; }
          uint32_t a[2][16];
          const uint32_t l = fresh_lane();
          uint32_t fa[4];
#pragma unroll
          for (int kk = 0; kk < 4; kk++) fa[kk] = (base + wg * 8192 + frag_offset(warp)) ^ (kk * 32);
          const uint32_t mt = par + (l & 3) * 16;
          auto fetch = [&](int i, uint32_t (&f)[16], uint32_t z) {
            mbar_wait(xfull + (i & 3) * 8, i >> 2);
#pragma unroll
            for (int kk = 0; kk < 4; kk++) ldmatrix4(fa[kk] + (i & 3) * GST_BYTES + z, f[4 * kk], f[4 * kk + 1], f[4 * kk + 2], f[4 * kk + 3]);
          };
          const bool oddw = warp & 2;
          uint4 r0, r1;
          {
            const uint32_t t7 = (warp & 1) * 64 + (l >> 4) * 32 + (l & 15);
            const uint32_t* pm = g_modp + wg * DM + ((cj * 128 + t7 * 4) & (DM - 1));
            const uint32_t* pr = g_ln1 + (rb * 128 + warp * 16 + (l >> 2)) * 4;
            uint4 m0 = make_uint4(tag, tag, tag, tag), m1 = m0;
            if (!oddw) { m0 = ld_relaxed4(pm); m1 = ld_relaxed4(pm + 2 * DM); }
            r0 = ld_b128(pr); r1 = ld_b128(pr + 32);
            fetch(0, a[0], 0); fetch(1, a[1], 0);
            uint32_t n = 0;
            bool written = false;
#pragma unroll 1
            while (true) {
              uint32_t miss;
              asm volatile("{ .reg .pred p0, p1, p2, p3; .reg .b32 t, u;\n"
                           "lop3.b32 t, %1, %2, %19, 0x7e; lop3.b32 u, %3, %4, %19, 0x7e; or.b32 t, t, u; and.b32 t, t, 3; setp.ne.u32 p0, t, 0;\n"
                           "lop3.b32 t, %5, %6, %19, 0x7e; lop3.b32 u, %7, %8, %19, 0x7e; or.b32 t, t, u; and.b32 t, t, 3; setp.ne.u32 p1, t, 0;\n"
                           "setp.ne.u32 p2, %12, %19; setp.ne.u32 p3, %16, %19;\n"
                           "@p0 ld.relaxed.gpu.global.v4.u32 {%1, %2, %3, %4}, [%17];\n"
                           "@p1 ld.relaxed.gpu.global.v4.u32 {%5, %6, %7, %8}, [%17 + 8192];\n"
                           "@p2 ld.relaxed.gpu.global.v4.u32 {%9, %10, %11, %12}, [%18];\n"
                           "@p3 ld.relaxed.gpu.global.v4.u32 {%13, %14, %15, %16}, [%18 + 128];\n"
                           "or.pred p0, p0, p1; or.pred p2, p2, p3; vote.sync.any.pred p0, p0, 0xffffffff; vote.sync.any.pred p2, p2, 0xffffffff;\n"
                           "selp.u32 t, 1, 0, p0; selp.u32 u, 2, 0, p2; or.b32 %0, t, u; }"
                           : "=r"(miss), "+r"(m0.x), "+r"(m0.y), "+r"(m0.z), "+r"(m0.w), "+r"(m1.x), "+r"(m1.y), "+r"(m1.z), "+r"(m1.w),
                             "+r"(r0.x), "+r"(r0.y), "+r"(r0.z), "+r"(r0.w), "+r"(r1.x), "+r"(r1.y), "+r"(r1.z), "+r"(r1.w)
                           : "l"(pm), "l"(pr), "r"(tag) : "memory");
              if (!(miss & 1) && !written) {
                written = true;
                if (!oddw) write_table(par, wg, t7, m0, m1);
                mbar_arrive(bar_mod);
              }
              if (!miss) break;
              watchdog(n);
            }
          }
          const uint32_t zero = r0.w ^ tag;
          auto normalize = [&](uint32_t (&f)[16]) {
#pragma unroll
            for (int k = 0; k < 16; k += 2) { f[k] = ln_norm(f[k], r0.x, r0.y, r0.z); f[k + 1] = ln_norm(f[k + 1], r1.x, r1.y, r1.z); }
          };
          auto modulate = [&](int i, uint32_t (&f)[16]) {
#pragma unroll
            for (int kk = 0; kk < 4; kk++) {
              const uint4 m = lds4(mt + slice_of(i) * 256 + kk * 64);
              f[4 * kk] = MODUL(f[4 * kk], m.x, m.z); f[4 * kk + 1] = MODUL(f[4 * kk + 1], m.x, m.z);
              f[4 * kk + 2] = MODUL(f[4 * kk + 2], m.y, m.w); f[4 * kk + 3] = MODUL(f[4 * kk + 3], m.y, m.w);
            }
            keep(f);
            mbar_arrive_pred(xempty + (i & 3) * 8, l == 0);
          };
          auto publish = [&](int u, uint32_t (&f)[16]) {
#pragma unroll
            for (int kk = 0; kk < 4; kk++) stmatrix4(fa[kk] + OFF_STAGE + u * UNIT, f[4 * kk], f[4 * kk + 1], f[4 * kk + 2], f[4 * kk + 3]);
            __syncwarp();
            mbar_arrive_pred(bar_hpub + u * 8, l == 0);
          };
          auto multiply = [&](int i, uint32_t (&f)[16]) {
            mbar_wait(gfull + (i & 3) * 8, i >> 2);
            const uint64_t db = make_desc(base + (i & 3) * GST_BYTES + UNIT, 8192, 1024);
            wg_fence();
#pragma unroll
            for (int kk = 0; kk < 4; kk++) mma256_rs(ga, gb, f[4 * kk], f[4 * kk + 1], f[4 * kk + 2], f[4 * kk + 3], db + kk * 128);
            wg_commit();
          };
          auto next = [&](int i, uint32_t (&f)[16]) {
            wg_wait<1>();
            mbar_arrive_cl(rempty, GE + ((i + 2) & 3) * 8);
            uint32_t z = zero;
#pragma unroll
            for (int k = 0; k < 16; k += 2) asm volatile("lop3.b32 %0, %1, %2, %0, 0xA8;" : "+r"(z) : "r"(f[k]), "r"(f[k + 1]));
            fetch(i, f, z);
            normalize(f);
            if (i == 2) { keep(f); mbar_wait(bar_mod2, 0); }
            modulate(i, f); multiply(i, f);
          };
          normalize(a[0]); normalize(a[1]);
          keep(a[0]); keep(a[1]);
          mbar_wait(bar_mod, 0);
          PROF(1, tid == 0, 2);
          modulate(0, a[0]); multiply(0, a[0]); publish(0, a[0]);
          modulate(1, a[1]); multiply(1, a[1]);
#pragma unroll 1
          for (int i = 2; i < NRS; i += 2) {
            next(i, a[0]);
            if (i == 2) publish(1, a[0]);
            next(i + 1, a[1]);
          }
          wg_wait<1>();
          mbar_arrive_cl(rempty, GE + ((NRS + 2) & 3) * 8);
#pragma unroll 1
          for (int i = NRS; i < 14; i++) {
            mbar_wait(xfull + (i & 3) * 8, (i >> 2) & 1);
            mbar_wait(gfull + (i & 3) * 8, (i >> 2) & 1);
            const uint32_t xa = base + (i & 3) * GST_BYTES;
            const uint64_t da = make_desc(xa + wg * 8192, 16, 1024), db = make_desc(xa + UNIT, 8192, 1024);
            if (i == 13) bar_sync(2 + wg, 256);
            wg_fence();
#pragma unroll
            for (int kk = 0; kk < 4; kk++) mma256_ss(ga, gb, da + kk * 2, db + kk * 128, 1);
            wg_commit();
            if (i == 13) bar_arrive(3 - wg, 256);
            wg_wait<1>();
            uint32_t z = zero;
#pragma unroll
            for (int k = 0; k < 16; k += 2) asm volatile("lop3.b32 %0, %1, %2, %0, 0xA8;" : "+r"(z) : "r"(a[1][k]), "r"(a[1][k + 1]));
            mbar_arrive_cl(rempty, GE + ((i + 3) & 3) * 8 + z);
            mbar_arrive_pred(xempty + ((i + 3) & 3) * 8, l == 0 && i != NRS);
          }
          mbar_wait(xfull + 16, 1);
          wg_wait<0>();
          keep(ga); keep(gb);
#pragma unroll
          for (int i = 0; i < 64; i++) {
            asm volatile("mov.b32 %0, %1;" : "=f"(s[i]) : "f"(ga[i]));
            asm volatile("mov.b32 %0, %1;" : "=f"(o[i]) : "f"(gb[i]));
          }
        } else {
          float ga[64], gb[64];
#pragma unroll
          for (int i = 0; i < 64; i++) {
            asm volatile("mov.b32 %0, %1;" : "=f"(ga[i]) : "f"(s[i]));
            asm volatile("mov.b32 %0, %1;" : "=f"(gb[i]) : "f"(o[i]));
          }
#pragma unroll 1
          for (int i = 0; i < nst; i++) {
            mbar_wait(gfull + (i & 3) * 8, (i >> 2) & 1);
            const uint64_t da = make_desc(base + unit_of(xt, i & 3) + wg * 8192, 16, 1024), db = make_desc(base + unit_of(wt, i & 3), 8192, 1024);
            if (i == nst - 1) bar_sync(2 + wg, 256);
            wg_fence();
#pragma unroll
            for (int kk = 0; kk < 4; kk++) mma256_ss(ga, gb, da + kk * 2, db + kk * 128, kk ? 1 : i);
            wg_commit();
            if (i == nst - 1) bar_arrive(3 - wg, 256);
            wg_wait<1>();
            mbar_arrive_cl(rempty, GE + ((i + 3) & 3) * 8, i != 0);
            PROF(4, tid == 0 && (i & 3) == 0, 40 + (ps - 1) * 4 + i / 4);
          }
          wg_wait<0>();
          keep(ga); keep(gb);
#pragma unroll
          for (int i = 0; i < 64; i++) {
            asm volatile("mov.b32 %0, %1;" : "=f"(s[i]) : "f"(ga[i]));
            asm volatile("mov.b32 %0, %1;" : "=f"(o[i]) : "f"(gb[i]));
          }
        }
        mbar_arrive_cl(rempty, GE + (ps == 2 ? 24 : 8));
        if (ps == 2) break;
      }
      const uint32_t qw = base + wg * 8192, qt = QT >> (16 * ps), at = ps ? AT1 : AT0;
      {
        const uint32_t wt = ps ? WT1 : WT0;
        const uint64_t da0 = make_desc(qw + unit_of(qt, 2), 16, 1024), da1 = make_desc(qw + unit_of(qt, 3), 16, 1024);
        const uint64_t db0 = make_desc(base + unit_of(wt, 2), 8192, 1024), db1 = make_desc(base + unit_of(wt, 3), 8192, 1024);
        mbar_wait(gfull + 16, 1);
        bar_sync(2 + wg, 256);
        wg_fence();
#pragma unroll
        for (int kk = 0; kk < 4; kk++) mma_ss<1>(s, da0 + kk * 2, db0 + kk * 128, 1);
        wg_commit();
        mbar_wait(xfull + 24, 1);
        mbar_wait(gfull + 24, 1);
        wg_fence();
#pragma unroll
        for (int kk = 0; kk < 4; kk++) mma_ss<1>(s, da1 + kk * 2, db1 + kk * 128, 1);
        wg_commit();
        bar_arrive(3 - wg, 256);
        mbar_wait(ps == 0 ? bar_pread : bar_ofree + 8, 0);
        wg_wait<0>();
        keep(s);
        PROF(2, tid == 0, 8 + ps * 8);
        uint32_t q[32];
        pack_p(s, q);
#pragma unroll
        for (int i = 0; i < 4; i++) stmatrix4((qw + unit_of(qt, 0) + frag_offset(warp)) ^ (i << 5), q[4 * i], q[4 * i + 1], q[4 * i + 2], q[4 * i + 3]);
        keep(q);
        bar_sync(2 + wg, 256);
        wg_fence();
#pragma unroll
        for (int kk = 0; kk < 8; kk++) mma_ss<1>(o, (kk < 4 ? da0 : da1) + (kk & 3) * 2, (kk < 4 ? db0 : db1) + UNIT / 16 + (kk & 3) * 128, 1);
        wg_commit();
        mbar_wait(bfull, 0);
        wg_fence();
        const uint64_t dk = make_desc(base + unit_of(at, 0), 16, 1024);
#pragma unroll
        for (int kk = 0; kk < 8; kk++) mma_rs<0>(s, q[4 * kk], q[4 * kk + 1], q[4 * kk + 2], q[4 * kk + 3], dk + (kk >> 2) * 1024 + (kk & 3) * 2, kk != 0);
        wg_commit();
        bar_arrive(3 - wg, 256);
#pragma unroll
        for (int i = 4; i < 8; i++) stmatrix4((qw + unit_of(qt, 1) + frag_offset(warp)) ^ ((i & 3) << 5), q[4 * i], q[4 * i + 1], q[4 * i + 2], q[4 * i + 3]);
        wg_wait<1>();
        keep(o);
        mbar_arrive_cl(rempty, GE + 16);
        mbar_arrive_cl(rempty, GE + 24);
        store_chunk<0>(o, qw + unit_of(qt, 2) + frag_offset(warp));
        store_chunk<1>(o, qw + unit_of(qt, 3) + frag_offset(warp));
        wg_wait<0>();
        keep(s);
        mbar_arrive_cl(rempty, 0);
      }
      PROF(4, tid == 0 && ps == 1, 61);
      float l0 = 0.f, l1 = 0.f;
      auto step = [&](auto odd_c, const int j, uint32_t (&pw)[32], uint32_t (&pr)[32]) {
        constexpr bool ODD = decltype(odd_c)::value;
        const bool first = !ODD && (j & 2) == 0, last = ODD && j == 7;
        const uint32_t ph = (j >> 1) & 1;
        float i0, i1, a0, a1;
        const bool so = !ODD && j == 4;
        if (so) { i0 = inv_quad_sum(l0); i1 = inv_quad_sum(l1); l0 = 0.f; l1 = 0.f; }
        bool redo = !ODD && (j | ps) == 0;
        while (true) {
          if (redo) {
            float m0 = fmaxf(s[0], s[1]), m1 = fmaxf(s[2], s[3]);
#pragma unroll
            for (int i = 1; i < 16; i++) { m0 = fmaxf(m0, fmaxf(s[4 * i], s[4 * i + 1])); m1 = fmaxf(m1, fmaxf(s[4 * i + 2], s[4 * i + 3])); }
            m0 = fmaxf(m0, __shfl_xor_sync(0xffffffffu, m0, 1)); m1 = fmaxf(m1, __shfl_xor_sync(0xffffffffu, m1, 1));
            m0 = fmaxf(m0, __shfl_xor_sync(0xffffffffu, m0, 2)); m1 = fmaxf(m1, __shfl_xor_sync(0xffffffffu, m1, 2));
            m0 *= SCL2; m1 *= SCL2;
            if (!first) {
              m0 = fmaxf(m0, f0); m1 = fmaxf(m1, f1);
              const float c0 = ex2(f0 - m0), c1 = ex2(f1 - m1);
              l0 *= c0; l1 *= c1;
              wg_wait<0>();
              keep(o);
#pragma unroll
              for (int i = 0; i < 16; i++) { o[4 * i] *= c0; o[4 * i + 1] *= c0; o[4 * i + 2] *= c1; o[4 * i + 3] *= c1; }
            }
            f0 = m0; f1 = m1;
          }
          float b0 = 0.f, b1 = 0.f;
          a0 = 0.f; a1 = 0.f;
#pragma unroll
          for (int i = 0; i < 16; i++) {
            const float e0 = ex2(fmaf(s[4 * i], SCL2, -f0)), e1 = ex2(fmaf(s[4 * i + 1], SCL2, -f0));
            const float e2 = ex2(fmaf(s[4 * i + 2], SCL2, -f1)), e3 = ex2(fmaf(s[4 * i + 3], SCL2, -f1));
            a0 += e0; b0 += e1; a1 += e2; b1 += e3;
            pw[2 * i] = pack_bf(e0, e1); pw[2 * i + 1] = pack_bf(e2, e3);
            if (i == VREL) {
#pragma unroll
              for (int k = 0; k < 2 * VREL + 2; k++) asm volatile("" : "+r"(pw[k])::"memory");
              mbar_wait(bar_mod, 0);
              wg_wait<0>();
              mbar_arrive_cl(rempty, ODD ? 16 : 0, !redo && (ODD || j));
#pragma unroll
              for (int k = 4 * VREL + 4; k < 64; k++) asm volatile("" : "+f"(s[k])::"memory");
            }
          }
          a0 += b0; a1 += b1;
          if (redo) break;
          redo = __any_sync(0xffffffffu, !(a0 + a1 < 0x1p90f));
          if (first) {
            uint32_t m0 = __ballot_sync(0xffffffffu, a0 > 0x1p-80f), m1 = __ballot_sync(0xffffffffu, a1 > 0x1p-80f);
            m0 |= m0 >> 1; m1 |= m1 >> 1; m0 |= m0 >> 2; m1 |= m1 >> 2;
            redo = redo || (m0 & m1 & 0x11111111u) != 0x11111111u;
          }
          if (!redo) break;
        }
        l0 += a0; l1 += a1;
        keep(pw);
        keep(o);
        if (so) store_chunk<0>(o, i0, i1, qw + unit_of(qt, 0) + frag_offset(warp));
        keep(o);
        if (j == (ODD ? 5 : 0)) { fence_async_smem(); if (ODD) mbar_arrive(bar_ofull + wg * 8); }
        mbar_wait(bfull + (ODD ? 24 : 8), ph);
        bar_sync(2 + wg, 256);
        if (!last) {
          const uint32_t qn = qt >> (j >= 3 ? 8 : 0);
          wg_fence();
          issue_qk(s, qw + unit_of(qn, 0), qw + unit_of(qn, 1), base + unit_of(at, ODD ? 3 : 1));
          wg_commit();
          mbar_wait(bfull + (ODD ? 0 : 16), ODD ? ph ^ 1 : ph);
        }
        if (so) { store_chunk<1>(o, i0, i1, qw + unit_of(qt, 1) + frag_offset(warp)); keep(o); }
        wg_fence();
        issue_pv(o, pw, base + unit_of(at, ODD ? (last ? 3 : 0) : 2), !first);
        wg_commit();
        bar_arrive(3 - wg, 256);
        wg_wait<1>();
        keep(s);
        mbar_arrive_cl(rempty, ODD ? 24 : 8, !last);
        PROF(4, tid == 0 && ps == 1, 51 + j);
      };
      uint32_t pa[32], pb[32];
#pragma unroll 1
      for (int j = 0; j < 8; j += 2) {
        step(std::false_type{}, j, pa, pb);
        step(std::true_type{}, j + 1, pb, pa);
      }
      {
        const float i0 = inv_quad_sum(l0), i1 = inv_quad_sum(l1);
        wg_wait<0>();
        keep(o);
        mbar_arrive_cl(rempty, 24);
        store_chunk<0>(o, i0, i1, qw + unit_of(qt, 2) + frag_offset(warp));
        store_chunk<1>(o, i0, i1, qw + unit_of(qt, 3) + frag_offset(warp));
        fence_async_smem();
        mbar_arrive(bar_ofull + 16 + wg * 8);
      }
      PROF(2, tid == 0, 10 + ps * 8);
    }

    const int ln = fresh_lane(), g = ln >> 2, tq = ln & 3, ct = warp * 32 + ln;
    const bool lane0 = ln == 0;
    const int lrow0 = warp * 16 + g;
    const int grow0 = rb * 128 + lrow0;
    const uint32_t res = base + OFF_RES, trow = res + wg * 8192 + frag_offset(warp);
    uint32_t xr[32];
    uint4 sv[4], own;
    uint32_t* sp[4];
#pragma unroll
    for (int k = 0; k < 4; k++) sp[k] = g_stats + ((((tq >> 1) * 4 + k) ^ cj) * SEQ + grow0 + (tq & 1) * 8) * 4;
    {
      const uint64_t da = make_desc(base + wg * 8192, 16, 1024), db = make_desc(base, 8192, 1024);
      constexpr int U = UNIT / 16;
#define HALF_STAGE(acc, xu, wu) _Pragma("unroll") for (int kk = 0; kk < 4; kk++) mma_ss<1>(acc, da + (xu) * U + kk * 2, db + (wu) * U + kk * 128, 1)
      PROF(10, ct == PT, 19); STAMP(0);
      cluster_arrive();
      mbar_wait(gfull, 1);
      mbar_wait(gfull + 8, 1);
      bar_sync(2 + wg, 256);
      wg_fence();
      HALF_STAGE(o, 7, 1);
      HALF_STAGE(o, 8, 3);
      wg_commit();
      STAMP(16);
      mbar_wait(gfull + 16, 1);
      STAMP(17);
      wg_fence();
      HALF_STAGE(o, 6, 11);
      wg_commit();
      bar_arrive(3 - wg, 256);
      mbar_wait(bar_par, 0);
      uint32_t* xo = g_xch + ((size_t)b * 8 * 256 + ct) * 4;
      const uint32_t* xi = g_xch + ((size_t)(b ^ 2) * 8 * 256 + ct) * 4;
      const uint32_t par1 = (~lds1(par + PAR_CONST + 4) & 1) << 16;
      wg_wait<1>();
      mbar_arrive_pred(bar_rel, lane0);
      wg_wait<0>();
      keep(o);
      mbar_arrive_pred(bar_ring, lane0);
      PROF(8, ct == PT, 20); STAMP(1);
#define SEND(i) st_b128(xo + (i) * 1024, (pack_bf(o[8 * (i)], o[8 * (i) + 1]) & ~0x10000u) | par1, pack_bf(o[8 * (i) + 2], o[8 * (i) + 3]), \
                        pack_bf(o[8 * (i) + 4], o[8 * (i) + 5]), pack_bf(o[8 * (i) + 6], o[8 * (i) + 7]))
#pragma unroll
      for (int i = 0; i < NS1; i++) SEND(i);
      PROF(8, ct == PT, 21); STAMP(2);
      bar_sync(2 + wg, 256);
      wg_fence();
      HALF_STAGE(s, 7, 0);
      HALF_STAGE(s, 8, 2);
      HALF_STAGE(s, 6, 10);
      wg_commit();
      bar_arrive(3 - wg, 256);
      STAMP(18);
      mbar_wait(gfull + 24, 1);
#pragma unroll
      for (int i = NS1; i < 8; i++) SEND(i);
      uint4 v[8];
#pragma unroll
      for (int i = 0; i < LD1; i++) v[i] = ld_b128(xi + i * 1024);
      STAMP(19);
      mbar_wait(bar_xres, 0);
      wg_wait<0>();
      mbar_arrive_pred(bar_ring + 8, lane0);
      bar_sync(2 + wg, 256);
      STAMP(20);
#pragma unroll
      for (int i = LD1; i < LD2; i++) v[i] = ld_b128(xi + i * 1024);
      mbar_wait(bar_xres, 0);
      wg_fence();
      HALF_STAGE(s, 9, 4);
      wg_commit();
      mbar_wait(bar_rx, 0);
      wg_fence();
      HALF_STAGE(s, 1, 5);
      wg_commit();
      bar_arrive(3 - wg, 256);
      STAMP(21);
#pragma unroll
      for (int i = LD2; i < 8; i++) v[i] = ld_b128(xi + i * 1024);
      if (LD2 < 8) mbar_wait(bar_xres, 0);
      wg_wait<0>();
      keep(s);
      mbar_arrive_pred(bar_ring + 16, lane0);
      PROF(10, ct == PT, 23); STAMP(4);
#pragma unroll
      for (int i = 0; i < 16; i += 2) ldmatrix4((trow ^ ((i & 7) << 4)) + (i >> 3) * 16384, xr[2 * i], xr[2 * i + 1], xr[2 * i + 2], xr[2 * i + 3]);
      uint32_t ga[16];
      uint4 bw[8];
#pragma unroll
      for (int i = 0; i < 8; i++) {
        if (!(i & 1)) {
          const uint4 t = lds4(par + PAR_SINK + i * 32 + tq * 16);
          ga[2 * i] = t.x; ga[2 * i + 1] = t.y; ga[2 * i + 2] = t.z; ga[2 * i + 3] = t.w;
        }
        bw[i] = lds4(par + PAR_T1 + i * 64 + tq * 16);
        if (!(g & 1)) { bw[i].x = 0x3f803f80u; bw[i].y = 0x3f803f80u; }
      }
      uint32_t pk[32];
      pack_p(s, pk);
      keep(pk);
      {
        uint32_t n = 0, miss;
        do {
          miss = 0;
#pragma unroll
          for (int i = 0; i < 8; i++) miss |= v[i].x ^ par1;
          miss = __any_sync(0xffffffffu, miss & 0x10000u);
          if (miss) {
#pragma unroll
            for (int i = 0; i < 8; i++)
              asm volatile("{ .reg .pred p; .reg .b32 t; xor.b32 t, %0, %5; and.b32 t, t, 0x10000; setp.ne.u32 p, t, 0;\n"
                           "@p ld.relaxed.gpu.global.v4.u32 {%0, %1, %2, %3}, [%4]; }"
                           : "+r"(v[i].x), "+r"(v[i].y), "+r"(v[i].z), "+r"(v[i].w) : "l"(xi + i * 1024), "r"(par1) : "memory");
          }
          watchdog(n);
        } while (miss);
      }
      PROF(8, ct == PT, 22); STAMP(3);
      float ds[4] = {0.f, 0.f, 0.f, 0.f}, dl[4] = {0.f, 0.f, 0.f, 0.f}, q0[4] = {0.f, 0.f, 0.f, 0.f}, q1[4] = {0.f, 0.f, 0.f, 0.f};
#pragma unroll
      for (int i = 0; i < 8; i++) {
        const uint32_t u0 = hfma2(ga[2 * i], hadd2(pk[4 * i], v[i].x & ~0x10000u), xr[4 * i]);
        const uint32_t u1 = hfma2(ga[2 * i], hadd2(pk[4 * i + 1], v[i].y), xr[4 * i + 1]);
        const uint32_t u2 = hfma2(ga[2 * i + 1], hadd2(pk[4 * i + 2], v[i].z), xr[4 * i + 2]);
        const uint32_t u3 = hfma2(ga[2 * i + 1], hadd2(pk[4 * i + 3], v[i].w), xr[4 * i + 3]);
        xr[4 * i] = u0; xr[4 * i + 1] = u1; xr[4 * i + 2] = u2; xr[4 * i + 3] = u3;
        mma16816(ds, u0, u1, u2, u3, bw[i].x, bw[i].y);
        mma16816(dl, u0, u1, u2, u3, bw[i].z, bw[i].w);
        mma16816(q0, u0, u1, u2, u3, u0, u2);
        mma16816(q1, u0, u1, u2, u3, u1, u3);
      }
      const float sqa = __shfl_sync(0xffffffffu, (g & 1) ? q0[1] : q0[0], g * 4 + (g >> 1));
      const float sqb = __shfl_sync(0xffffffffu, (g & 1) ? q1[3] : q1[2], g * 4 + (g >> 1));
      own = (tq & 1) ? make_uint4(__float_as_uint(ds[2]), __float_as_uint(sqb), __float_as_uint(ds[3] + dl[3]), tag)
                                 : make_uint4(__float_as_uint(ds[0]), __float_as_uint(sqa), __float_as_uint(ds[1] + dl[1]), tag);
      if (tq < 2) st_b128(sp[0], own.x, own.y, own.z, own.w);
#pragma unroll
      for (int k = 0; k < 4; k++) sv[k] = make_uint4(0, 0, 0, 0);
    }
    PROF(8, ct == PT, 29); STAMP(5);
    uint32_t mm, ih, il;
    float rbest;
    uint32_t wf[128];
    const uint32_t frow = (ln & 7) + (ln >> 4) * 8;
    const uint32_t wfo = base + (warp & 1) * 8192 + frow * 64 + ((((ln >> 3) & 1) ^ ((frow >> 1) & 3)) << 4);
#define LOAD_WF(m) _Pragma("unroll") for (int f = 0; f < 16; f++) {                                                   \
      const int r = ((f >> 1) * 4 + (m) * 2 + (f & 1)) * 4;                                                           \
      ldmatrix4t(((wfo + unit_of((m) ? FT_U : FT_G, warp >> 1)) ^ ((f & 1) * 32)) + (f >> 1) * 1024, wf[r], wf[r + 1], wf[r + 2], wf[r + 3]); \
    }
    bool early;
    {
#pragma unroll
      for (int i = 0; i < 16; i += 2) stmatrix4((trow ^ ((i & 7) << 4)) + (i >> 3) * 16384, xr[2 * i], xr[2 * i + 1], xr[2 * i + 2], xr[2 * i + 3]);
      const uint4 cst = lds4(par + PAR_CONST);
      const float A1 = __uint_as_float(cst.x), A2 = __uint_as_float(cst.z);
      uint32_t n = 0;
      early = false;
#pragma unroll 1
      while (true) {
        uint32_t miss;
        asm volatile("{ .reg .pred p0, p1, p2, p3; .reg .b64 u, v; .reg .b128 w;\n"
                     "setp.ge.u32 p0, %22, 2; setp.ne.and.u32 p0, %4, %21, p0; setp.ne.u32 p1, %8, %21; setp.ne.u32 p2, %12, %21; setp.ne.u32 p3, %16, %21;\n"
                     "@p0 ld.relaxed.gpu.global.v4.u32 {%1, %2, %3, %4}, [%17];\n"
                     "@p1 ld.relaxed.gpu.global.v4.u32 {%5, %6, %7, %8}, [%18];\n"
                     "@p2 ld.relaxed.gpu.global.v4.u32 {%9, %10, %11, %12}, [%19];\n"
                     "@p3 ld.relaxed.gpu.global.v4.u32 {%13, %14, %15, %16}, [%20];\n"
                     "or.pred p0, p0, p1; or.pred p2, p2, p3; or.pred p0, p0, p2; vote.sync.any.pred p0, p0, 0xffffffff; selp.u32 %0, 1, 0, p0; }"
                     : "=r"(miss), "+r"(sv[0].x), "+r"(sv[0].y), "+r"(sv[0].z), "+r"(sv[0].w), "+r"(sv[1].x), "+r"(sv[1].y), "+r"(sv[1].z), "+r"(sv[1].w),
                       "+r"(sv[2].x), "+r"(sv[2].y), "+r"(sv[2].z), "+r"(sv[2].w), "+r"(sv[3].x), "+r"(sv[3].y), "+r"(sv[3].z), "+r"(sv[3].w)
                     : "l"(sp[0]), "l"(sp[1]), "l"(sp[2]), "l"(sp[3]), "r"(tag), "r"(tq) : "memory");
        if (!miss) break;
        if (!early && (b >= NFFN || __all_sync(0xffffffffu, mbar_test(bar_box + (warp >> 1) * 8, 0)))) {
          early = true;
          LOAD_WF(0);
          __syncwarp();
          mbar_arrive_pred(bar_gate, lane0);
        }
        watchdog(n);
      }
      const uint4 v0 = tq < 2 ? own : sv[0], v1 = sv[1], v2 = sv[2], v3 = sv[3];
      PROF(8, ct == PT, 30); STAMP(6);
      float su = (__uint_as_float(v0.x) + __uint_as_float(v1.x)) + (__uint_as_float(v2.x) + __uint_as_float(v3.x));
      float sq = (__uint_as_float(v0.y) + __uint_as_float(v1.y)) + (__uint_as_float(v2.y) + __uint_as_float(v3.y));
      float dt = (__uint_as_float(v0.z) + __uint_as_float(v1.z)) + (__uint_as_float(v2.z) + __uint_as_float(v3.z));
      su += __shfl_xor_sync(0xffffffffu, su, 2); sq += __shfl_xor_sync(0xffffffffu, sq, 2); dt += __shfl_xor_sync(0xffffffffu, dt, 2);
      const float m = su * (1.f / DM);
      float mb, sd;
      ln_scalars(m, fmaxf(sq * (1.f / DM) - m * m, 0.f), mb, sd);
      const float inv = rcp(sd);
      rbest = (dt - mb * A1) * inv + A2;
      mm = pack_bf(mb, mb);
      ih = pack_bf(inv, inv);
      const float lo = inv - bf_lo(ih);
      il = pack_bf(lo, lo);
    }
    int ibest;
    {
      const uint32_t bits = __float_as_uint(rbest);
      const uint32_t key = (((int)bits < 0 ? ~bits : bits | 0x80000000u) & ~0x1ffu) | ((127 - lrow0 - (tq & 1) * 8) << 2) | tag;
      sts1(par + PAR_RED + warp * 4, __reduce_max_sync(0xffffffffu, key));
      PROF(8, ct == PT, 38); STAMP(7);
      bar_sync(1, 256);
      const uint4 ka = lds4(par + PAR_RED), kb = lds4(par + PAR_RED + 16);
      const uint32_t k2 = max(max(max(ka.x, ka.y), max(ka.z, ka.w)), max(max(kb.x, kb.y), max(kb.z, kb.w)));
      if (ct < CR && cj == 0) st_relaxed(g_cand + ct * 512 + rb * CS, k2);
      ibest = 127 - ((k2 >> 2) & 127);
    }
    PROF(8, ct == PT, 39); STAMP(8);
    if ((ibest >> 4) == warp) {
      const int src = (ibest & 7) * 4 + ((ibest >> 3) & 1), ch = g * 2;
      const uint32_t cm = __shfl_sync(0xffffffffu, mm, src), ch_ = __shfl_sync(0xffffffffu, ih, src), cl = __shfl_sync(0xffffffffu, il, src);
      const uint32_t xa = res + (ch >> 3) * 16384 + ibest * 128 + (((ch & 7) ^ (ibest & 7)) << 4) + tq * 4;
      const uint32_t x0 = lds1(xa), x1 = lds1(xa ^ 16);
      const uint2 p0 = lds2(par + PAR_T2 + ch * 64 + tq * 16), p1 = lds2(par + PAR_T2 + ch * 64 + 64 + tq * 16);
      uint32_t* dst = g_row + rb * 2 * DM + cj * 128 + ln * 4;
      st_pairs(dst, ln_mod(x0, cm, ch_, cl, p0.x, p0.y), ln_mod(x1, cm, ch_, cl, p1.x, p1.y), tag);
      st_pairs(dst + DM, x0, x1, tag);
      __syncwarp();
    }
    PROF(8, ct == PT, 37); STAMP(9);
    uint32_t wd[64];
    const uint32_t wda = base + unit_of(FT_D, warp >> 1) + (warp & 1) * 8192 + frow * 128 + ((((ln >> 3) & 1) ^ (ln & 7)) << 4);
#define LOAD_WD(f) ldmatrix4t((wda ^ ((((f) >> 1) & 3) * 32)) + ((f) >> 3) * 4096 + ((f) & 1) * 2048, wd[4 * (f)], wd[4 * (f) + 1], wd[4 * (f) + 2], wd[4 * (f) + 3])
    if (!early) {
      if (b < NFFN) mbar_wait(bar_box + (warp >> 1) * 8, 0);
      LOAD_WF(0);
      __syncwarp();
      mbar_arrive_pred(bar_gate, lane0);
    }
    if (b < NFFN) {
      const uint32_t own = base + unit_of(FT_G, warp >> 1) + (warp & 1) * 8192;
      mbar_wait(bar_box + (4 + (warp >> 1)) * 8, 0);
      LOAD_WF(1);
      uint32_t* const ydst = ypart_slot(b, warp * 16 + (tq & 1) * 8 + g);
      PROF(8, ct == PT, 31); STAMP(10);
      bool wdok;
      {
        uint32_t n = 0;
        while (!(wdok = __all_sync(0xffffffffu, mbar_test(bar_box + (8 + (warp >> 1)) * 8, 0))) && !__all_sync(0xffffffffu, mbar_test(bar_sel, 0))) watchdog(n);
      }
      if (wdok) {
#pragma unroll
        for (int f = 0; f < 16; f++) LOAD_WD(f);
      }
      STAMP(11);
      mbar_wait(bar_sel, 0);
      PROF(8, ct == PT, 33); STAMP(12);
      float d[8][4];
#pragma unroll
      for (int i = 0; i < 4; i++) { d[i][0] = 0.f; d[i][1] = 0.f; d[i][2] = 0.f; d[i][3] = 0.f; }
#pragma unroll
      for (int ks = 0; ks < 8; ks++) {
        const uint2 hb = lds2(own + 256 + ks * 32 + tq * 8);
#pragma unroll
        for (int mt = 0; mt < 4; mt++) {
          const int r = ks * 16 + mt * 4;
          mma16816(d[mt], wf[r], wf[r + 1], wf[r + 2], wf[r + 3], hb.x, hb.y);
        }
      }
      sts2(own + (tq * 8 + g) * 8, __float_as_uint((tq & 2) ? ((tq & 1) ? d[1][2] : d[1][0]) : ((tq & 1) ? d[0][2] : d[0][0])),
           __float_as_uint((tq & 2) ? ((tq & 1) ? d[3][2] : d[3][0]) : ((tq & 1) ? d[2][2] : d[2][0])));
      bar_sync(1, 256);
      uint32_t ab[4];
      {
        float G = 0.f, U = 0.f;
        uint2 pv[8];
#pragma unroll
        for (int w8 = 0; w8 < 8; w8++) pv[w8] = lds2(base + ln * 8 + ((FT_G >> (w8 >> 1) * 4) & 15) * UNIT + (w8 & 1) * 8192);
#pragma unroll
        for (int w8 = 0; w8 < 8; w8 += 2) {
          G += __uint_as_float(pv[w8].x) + __uint_as_float(pv[w8 + 1].x);
          U += __uint_as_float(pv[w8].y) + __uint_as_float(pv[w8 + 1].y);
        }
        const float act = rbf(silu_f(rbf(G))) * rbf(U);
        const uint32_t pk = pack_bf(act, __shfl_down_sync(0xffffffffu, act, 1));
#pragma unroll
        for (int i = 0; i < 4; i++) ab[i] = __shfl_sync(0xffffffffu, pk, i * 8 + tq * 2);
      }
      if (!wdok) {
        mbar_wait(bar_box + (8 + (warp >> 1)) * 8, 0);
#pragma unroll
        for (int f = 0; f < 16; f++) LOAD_WD(f);
      }
      PROF(8, ct == PT, 34); STAMP(13);
#pragma unroll
      for (int mt = 0; mt < 8; mt++) {
        d[mt][0] = 0.f; d[mt][1] = 0.f; d[mt][2] = 0.f; d[mt][3] = 0.f;
        mma16816(d[mt], wd[mt * 8], wd[mt * 8 + 1], wd[mt * 8 + 2], wd[mt * 8 + 3], ab[0], ab[1]);
        mma16816(d[mt], wd[mt * 8 + 4], wd[mt * 8 + 5], wd[mt * 8 + 6], wd[mt * 8 + 7], ab[2], ab[3]);
      }
      uint32_t yw[4];
#pragma unroll
      for (int i = 0; i < 4; i++) yw[i] = (tq & 1) ? pack_bf(d[2 * i][2], d[2 * i + 1][2]) : pack_bf(d[2 * i][0], d[2 * i + 1][0]);
      if (tq < 2) st_b128(ydst, (yw[0] & ~1u) | (tag & 1), (yw[1] & ~1u) | (tag >> 1), yw[2], yw[3]);
      PROF(8, ct == PT, 35); STAMP(14);
    }
    mbar_wait(bar_sel, 0);
    mbar_arrive_pred(bar_win, ct == 0);
    const int iwin = lds1(par + PAR_CONST + 60) & 0x7ff;
    const bool cand = (iwin >> 4) == rb * 8 + warp;
    {
      const uint32_t mm0 = __shfl_sync(0xffffffffu, mm, ln & ~1), mm1 = __shfl_sync(0xffffffffu, mm, ln | 1);
      const uint32_t ih0 = __shfl_sync(0xffffffffu, ih, ln & ~1), ih1 = __shfl_sync(0xffffffffu, ih, ln | 1);
      const uint32_t il0 = __shfl_sync(0xffffffffu, il, ln & ~1), il1 = __shfl_sync(0xffffffffu, il, ln | 1);
#pragma unroll OUR
      for (int hf = 0; hf < 2; hf++) {
        uint32_t x[16];
#pragma unroll
        for (int i = 0; i < 8; i += 2) ldmatrix4((trow ^ (i << 4)) + hf * 16384, x[2 * i], x[2 * i + 1], x[2 * i + 2], x[2 * i + 3]);
#pragma unroll
        for (int i = 0; i < 8; i++) {
          const uint4 pv = lds4(par + PAR_T2 + (hf * 8 + i) * 64 + tq * 16);
          x[2 * i] = hfma2(hfma2(ln_norm(x[2 * i], mm0, ih0, il0), pv.x, pv.y), pv.z, x[2 * i]);
          x[2 * i + 1] = hfma2(hfma2(ln_norm(x[2 * i + 1], mm1, ih1, il1), pv.x, pv.y), pv.z, x[2 * i + 1]);
        }
#pragma unroll
        for (int i = 0; i < 8; i += 2) stmatrix4((trow ^ (i << 4)) + hf * 16384, x[2 * i], x[2 * i + 1], x[2 * i + 2], x[2 * i + 3]);
        if (!cand) fence_async_smem();
        __syncwarp();
        if (!cand && elect_one()) {
          tma2d_store(&maps.out, res + hf * 16384 + warp * 2048, cj * 128 + hf * 64, rb * 128 + warp * 16);
          asm volatile("cp.async.bulk.commit_group;" ::: "memory");
        }
      }
    }
    if (cand) {
      const int wrow0 = warp * 16;
#pragma unroll 2
      for (int p = 0; p < 8; p++) {
        const int row = 2 * p + (ln >> 4), ch = ln & 15;
        const uint4 v = lds4(res + (ch >> 3) * 16384 + (wrow0 + row) * 128 + (((ch & 7) ^ (row & 7)) << 4));
        if (rb * 128 + wrow0 + row != iwin) *reinterpret_cast<uint4*>(P.out + (size_t)(rb * 128 + wrow0 + row) * DM + cj * 128 + ch * 8) = v;
      }
    }
    asm volatile("cp.async.bulk.wait_group.read 0;" ::: "memory");
    PROF(8, ct == PT, 11); STAMP(15);
    cluster_wait();
  }
}

typedef CUresult (*EncodeFn)(CUtensorMap*, CUtensorMapDataType, cuuint32_t, void*, const cuuint64_t*, const cuuint64_t*,
                             const cuuint32_t*, const cuuint32_t*, CUtensorMapInterleave, CUtensorMapSwizzle,
                             CUtensorMapL2promotion, CUtensorMapFloatOOBfill);

void map2d(EncodeFn enc, CUtensorMap* m, const void* p, uint64_t rows, uint64_t cols, uint32_t brows) {
  cuuint64_t dims[2] = {cols, rows}, strides[1] = {cols * 2};
  cuuint32_t box[2] = {64, brows}, es[2] = {1, 1};
  enc(m, CU_TENSOR_MAP_DATA_TYPE_BFLOAT16, 2, const_cast<void*>(p), dims, strides, box, es, CU_TENSOR_MAP_INTERLEAVE_NONE,
      CU_TENSOR_MAP_SWIZZLE_128B, CU_TENSOR_MAP_L2_PROMOTION_L2_256B, CU_TENSOR_MAP_FLOAT_OOB_FILL_NONE);
}
void map2d_narrow(EncodeFn enc, CUtensorMap* m, const void* p, uint64_t rows, uint64_t cols, uint32_t brows) {
  cuuint64_t dims[2] = {cols, rows}, strides[1] = {cols * 2};
  cuuint32_t box[2] = {32, brows}, es[2] = {1, 1};
  enc(m, CU_TENSOR_MAP_DATA_TYPE_BFLOAT16, 2, const_cast<void*>(p), dims, strides, box, es, CU_TENSOR_MAP_INTERLEAVE_NONE,
      CU_TENSOR_MAP_SWIZZLE_64B, CU_TENSOR_MAP_L2_PROMOTION_L2_64B, CU_TENSOR_MAP_FLOAT_OOB_FILL_NONE);
}
void map3d(EncodeFn enc, CUtensorMap* m, const void* p, uint64_t rows, uint64_t cols, uint32_t brows, uint32_t nch) {
  cuuint64_t dims[3] = {64, rows, cols / 64}, strides[2] = {cols * 2, 128};
  cuuint32_t box[3] = {64, brows, nch}, es[3] = {1, 1, 1};
  enc(m, CU_TENSOR_MAP_DATA_TYPE_BFLOAT16, 3, const_cast<void*>(p), dims, strides, box, es, CU_TENSOR_MAP_INTERLEAVE_NONE,
      CU_TENSOR_MAP_SWIZZLE_128B, CU_TENSOR_MAP_L2_PROMOTION_L2_256B, CU_TENSOR_MAP_FLOAT_OOB_FILL_NONE);
}

}

extern "C" void kernel_launch(void* const* d_in, const int* in_sizes, int n_in, void* d_out, int out_size) {
  (void)in_sizes; (void)n_in; (void)out_size;
  static EncodeFn enc = nullptr;
  if (!enc) {
    void* fn = nullptr;
    cudaDriverEntryPointQueryResult st;
    cudaGetDriverEntryPoint("cuTensorMapEncodeTiled", &fn, cudaEnableDefault, &st);
    enc = (EncodeFn)fn;
    cudaFuncSetAttribute(fused_kernel, cudaFuncAttributeMaxDynamicSharedMemorySize, SMEM_BYTES);
  }
  Maps maps;
  map2d(enc, &maps.x, d_in[0], SEQ, DM, 128);
  map2d(enc, &maps.out, d_out, SEQ, DM, 16);
  map3d(enc, &maps.wq, d_in[3], DM, NQ, 64, 2);
  map3d(enc, &maps.k, d_in[1], 4 * SK, 128, 128, 1);
  map3d(enc, &maps.v, d_in[2], 4 * SK, 128, 128, 1);
  map3d(enc, &maps.wo, d_in[4], NQ, DM, 64, 2);
  map2d_narrow(enc, &maps.wg, d_in[7], DM, FF, 256);
  map2d_narrow(enc, &maps.wu, d_in[8], DM, FF, 256);
  map3d(enc, &maps.wd, d_in[9], FF, DM, 32, 4);
  map2d_narrow(enc, &maps.wm, d_in[11], DM, NMOD, 256);
  Ptrs p;
  p.x = (const __nv_bfloat16*)d_in[0];
  p.w_r = (const __nv_bfloat16*)d_in[6];
  p.w_gate = (const __nv_bfloat16*)d_in[7];
  p.w_up = (const __nv_bfloat16*)d_in[8];
  p.w_down = (const __nv_bfloat16*)d_in[9];
  p.c = (const __nv_bfloat16*)d_in[10];
  p.w_mod = (const __nv_bfloat16*)d_in[11];
  p.out = (__nv_bfloat16*)d_out;
  fused_kernel<<<NMAIN + NHELP, 384, SMEM_BYTES>>>(maps, p);
}
```

```cpp
#include <cuda_runtime.h>
#include <cuda_bf16.h>
#include <cuda.h>
#include <stdint.h>
#include <type_traits>

#define HD 2
#define HDX 2
#define NRS 8
#define FPACE 3
#define GOST 20
#define WB 2
#define WN 20
#define RES0 17
#define RES1 20
#define HU 32
#define NS1 5
#define PG0 15
#define FB0 0
#define FB2 8
#define OPS 8192
#define OFL 0
#define ODS 8
#define MODUL hfma2
#define ODS1 5
#define LD1 0
#define LD2 4
#define FB1 2
#define FPB 8
#define FPACE0 2
#define OSL 900
#define OSL2 400
#define CR 8
#define CS 8
#define OURV 1
#define VREL 5
#define E0 3

namespace {

constexpr int SEQ = 2048, DM = 1024, NQ = 4096, SK = 2048, WIN = 512, FF = 3584, NMOD = 6144;
constexpr int OUR = OURV;
constexpr int NMAIN = 128, NHELP = 4, NFFN = 112;
constexpr int NSLOT = 4, SLOT_BYTES = 32768, UNIT = 16384, GST_BYTES = 3 * UNIT;
constexpr uint32_t XT1 = 0xDCBA, XT2 = 0x9687;
constexpr uint32_t WT0 = 0xA741, WT1 = 0x7420, WT2 = 0x4A20;
constexpr uint32_t AT0 = WT1, AT1 = WT2;
constexpr uint32_t QT = 0xDC9696DC;
constexpr int OFF_STAGE = 12 * UNIT;
constexpr uint32_t FT_G = 0x07B3, FT_U = 0xA628, FT_D = 0x5149;
constexpr int OFF_RES = 12 * UNIT;
constexpr int OFF_PAR = 14 * UNIT;
constexpr int OFF_BAR = OFF_PAR + 2528;
constexpr int SMEM_BYTES = OFF_BAR + 544;
static_assert(SMEM_BYTES <= 232448, "smem");

constexpr int PAR_T1 = 0;
constexpr int PAR_T2 = 512;
constexpr int PAR_CONST = 1536;
constexpr int PAR_RED = 1600;
constexpr int PAR_SINK = 2176;

struct Maps {
  CUtensorMap x, wq, k, v, wo, wg, wu, wd, wm, out;
};
struct Ptrs {
  const __nv_bfloat16 *x, *w_r, *c, *w_mod, *w_gate, *w_up, *w_down;
  __nv_bfloat16* out;
};

__device__ __align__(1024) uint8_t g_act[16 * 80 * UNIT];
__device__ __align__(128) uint32_t g_mod[NMOD];
__device__ __align__(128) uint32_t g_modp[2 * 2 * DM];
__device__ __align__(128) uint32_t g_ln1[SEQ * 4];
__device__ __align__(128) uint32_t g_cnt_h[16 * 32];
__device__ __align__(128) uint32_t g_cnt_o[128 * 32];
__device__ __align__(128) uint32_t g_xch[NMAIN * 8 * 256 * 4];
__device__ __align__(128) uint32_t g_stats[8 * SEQ * 4];
__device__ __align__(128) uint32_t g_cand[CR * 512];
__device__ __align__(128) uint32_t g_row[16 * 2 * DM];
__device__ __align__(128) uint32_t g_ypart[NMAIN * NFFN * 4];
__device__ __forceinline__ uint32_t* ypart_slot(int writer, int reader) { return g_ypart + (writer * NMAIN + reader) * 4; }
__device__ uint32_t g_epoch;

__device__ __forceinline__ uint32_t fresh_lane() { uint32_t l; asm volatile("mov.u32 %0, %%laneid;" : "=r"(l)); return l; }
__device__ __forceinline__ uint32_t frag_offset(int warp) {
  const uint32_t l = fresh_lane();
  return ((warp & 3) * 16 + (l & 15)) * 128 + (((l >> 4) ^ (l & 7)) << 4);
}
__device__ __forceinline__ bool elect_one() {
  uint32_t p;
  asm volatile("{ .reg .pred q; elect.sync _|q, 0xffffffff; selp.u32 %0, 1, 0, q; }" : "=r"(p));
  return p;
}
__device__ __forceinline__ uint32_t smem_u32(const void* p) { return (uint32_t)__cvta_generic_to_shared(p); }
__device__ __forceinline__ void mbar_init(uint32_t bar, uint32_t cnt) {
  asm volatile("mbarrier.init.shared::cta.b64 [%0], %1;" ::"r"(bar), "r"(cnt) : "memory");
}
__device__ __forceinline__ void mbar_expect_tx(uint32_t bar, uint32_t bytes) {
  asm volatile("mbarrier.arrive.expect_tx.shared::cta.b64 _, [%0], %1;" ::"r"(bar), "r"(bytes) : "memory");
}
__device__ __forceinline__ void mbar_arrive(uint32_t bar) {
  asm volatile("mbarrier.arrive.shared::cta.b64 _, [%0];" ::"r"(bar) : "memory");
}
__device__ __forceinline__ void mbar_arrive_pred(uint32_t bar, bool p) {
  asm volatile("{ .reg .pred p; setp.ne.b32 p, %1, 0; @p mbarrier.arrive.shared::cta.b64 _, [%0]; }" ::"r"(bar), "r"((int)p) : "memory");
}
__device__ __forceinline__ void mbar_arrive_cl(uint32_t bar, uint32_t off, bool p = true) {
  asm volatile("{ .reg .pred p, q; .reg .b32 a; setp.ne.b32 q, %2, 0; setp.ne.and.b32 p, %0, 0, q; add.u32 a, %0, %1; @p mbarrier.arrive.shared::cluster.b64 _, [a]; }"
               ::"r"(bar), "r"(off), "r"((int)p) : "memory");
}
__device__ __forceinline__ uint32_t mapa(uint32_t addr, uint32_t cta) {
  uint32_t r; asm("mapa.shared::cluster.u32 %0, %1, %2;" : "=r"(r) : "r"(addr), "r"(cta)); return r;
}
__device__ __forceinline__ void cluster_arrive() { asm volatile("barrier.cluster.arrive.relaxed.aligned;" ::: "memory"); }
__device__ __forceinline__ void cluster_wait() { asm volatile("barrier.cluster.wait.aligned;" ::: "memory"); }
__device__ __forceinline__ void watchdog(uint32_t& n) {
}
__device__ __forceinline__ void mbar_wait(uint32_t bar, uint32_t parity) {
  asm volatile("{\n.reg .pred p;\nWAIT_%=:\nmbarrier.try_wait.parity.shared::cta.b64 p, [%0], %1;\n@!p bra WAIT_%=;\n}" ::"r"(bar), "r"(parity) : "memory");
}
__device__ __forceinline__ bool mbar_test(uint32_t bar, uint32_t parity) {
  uint32_t ok;
  asm volatile("{\n.reg .pred p;\nmbarrier.test_wait.parity.shared::cta.b64 p, [%1], %2;\nselp.u32 %0, 1, 0, p;\n}" : "=r"(ok) : "r"(bar), "r"(parity) : "memory");
  return ok;
}
__device__ __forceinline__ uint64_t l2_stream() {
  uint64_t f; asm("createpolicy.fractional.L2::evict_first.b64 %0, 1.0;" : "=l"(f)); return f;
}
__device__ __forceinline__ void tma2d(uint32_t dst, const CUtensorMap* m, int c0, int c1, uint32_t bar) {
  asm volatile("cp.async.bulk.tensor.2d.shared::cluster.global.mbarrier::complete_tx::bytes.L2::cache_hint [%0], [%1, {%3, %4}], [%2], %5;"
               ::"r"(dst), "l"(m), "r"(bar), "r"(c0), "r"(c1), "l"(l2_stream()) : "memory");
}
__device__ __forceinline__ void bulk_load(uint32_t dst, const void* src, uint32_t bytes, uint32_t bar) {
  asm volatile("cp.async.bulk.shared::cluster.global.mbarrier::complete_tx::bytes [%0], [%1], %2, [%3];" ::"r"(dst), "l"(src), "r"(bytes), "r"(bar) : "memory");
}
__device__ __forceinline__ void bulk_load_stream(uint32_t dst, const void* src, uint32_t bytes, uint32_t bar) {
  asm volatile("cp.async.bulk.shared::cluster.global.mbarrier::complete_tx::bytes.L2::cache_hint [%0], [%1], %2, [%3], %4;"
               ::"r"(dst), "l"(src), "r"(bytes), "r"(bar), "l"(l2_stream()) : "memory");
}
__device__ __forceinline__ void tma2d_store(const CUtensorMap* m, uint32_t src, int c0, int c1) {
  asm volatile("cp.async.bulk.tensor.2d.global.shared::cta.bulk_group [%0, {%2, %3}], [%1];" ::"l"(m), "r"(src), "r"(c0), "r"(c1) : "memory");
}
__device__ __forceinline__ void bulk_store(void* dst, uint32_t src, uint32_t bytes) {
  asm volatile("cp.async.bulk.global.shared::cta.bulk_group [%0], [%1], %2;" ::"l"(dst), "r"(src), "r"(bytes) : "memory");
}
__device__ __forceinline__ int slice_of(int i) { return i + ((i & 7) == 1) - ((i & 7) == 2); }
__device__ __forceinline__ uint32_t unit_of(uint32_t table, uint32_t i) { return ((table >> (i * 4)) & 15) * UNIT; }
__device__ __forceinline__ void tma3d(uint32_t dst, const CUtensorMap* m, int c0, int c1, int c2, uint32_t bar) {
  asm volatile("cp.async.bulk.tensor.3d.shared::cluster.global.mbarrier::complete_tx::bytes.L2::cache_hint [%0], [%1, {%3, %4, %5}], [%2], %6;"
               ::"r"(dst), "l"(m), "r"(bar), "r"(c0), "r"(c1), "r"(c2), "l"(l2_stream()) : "memory");
}
template <bool STREAM>
__device__ __forceinline__ void tma3d_mc(uint32_t dst, const CUtensorMap* m, int c0, int c1, int c2, uint32_t bar) {
  if (STREAM)
    asm volatile("cp.async.bulk.tensor.3d.shared::cluster.global.mbarrier::complete_tx::bytes.multicast::cluster.L2::cache_hint [%0], [%1, {%3, %4, %5}], [%2], %6, %7;"
                 ::"r"(dst), "l"(m), "r"(bar), "r"(c0), "r"(c1), "r"(c2), "h"((uint16_t)3), "l"(l2_stream()) : "memory");
  else
    asm volatile("cp.async.bulk.tensor.3d.shared::cluster.global.mbarrier::complete_tx::bytes.multicast::cluster [%0], [%1, {%3, %4, %5}], [%2], %6;"
                 ::"r"(dst), "l"(m), "r"(bar), "r"(c0), "r"(c1), "r"(c2), "h"((uint16_t)3) : "memory");
}
__device__ __forceinline__ void prefetch_map(const CUtensorMap* m) {
  asm volatile("prefetch.tensormap [%0];" ::"l"(m) : "memory");
}
__device__ __forceinline__ void fence_async() { asm volatile("fence.proxy.async.global;" ::: "memory"); }
__device__ __forceinline__ void fence_async_smem() { asm volatile("fence.proxy.async.shared::cta;" ::: "memory"); }
__device__ __forceinline__ void bar_sync(int id, int n) { asm volatile("bar.sync %0, %1;" ::"r"(id), "r"(n) : "memory"); }
__device__ __forceinline__ void bar_arrive(int id, int n) { asm volatile("bar.arrive %0, %1;" ::"r"(id), "r"(n) : "memory"); }
__device__ __forceinline__ void wg_fence() { asm volatile("wgmma.fence.sync.aligned;" ::: "memory"); }
__device__ __forceinline__ void wg_commit() { asm volatile("wgmma.commit_group.sync.aligned;" ::: "memory"); }
template <int N> __device__ __forceinline__ void wg_wait() { asm volatile("wgmma.wait_group.sync.aligned %0;" ::"n"(N) : "memory"); }
__device__ __forceinline__ uint64_t make_desc(uint32_t addr, uint32_t lbo, uint32_t sbo) {
  return (uint64_t)((addr & 0x3FFFF) >> 4) | ((uint64_t)(lbo >> 4) << 16) | ((uint64_t)(sbo >> 4) << 32) | (1ull << 62);
}
__device__ __forceinline__ uint32_t ld_relaxed(const uint32_t* p) {
  uint32_t v; asm volatile("ld.relaxed.gpu.global.u32 %0, [%1];" : "=r"(v) : "l"(p) : "memory"); return v;
}
__device__ __forceinline__ uint32_t ld_acquire(const uint32_t* p) {
  uint32_t v; asm volatile("ld.acquire.gpu.global.u32 %0, [%1];" : "=r"(v) : "l"(p) : "memory"); return v;
}
__device__ __forceinline__ uint4 ld_relaxed4(const uint32_t* p) {
  uint4 v; asm volatile("ld.relaxed.gpu.global.v4.u32 {%0,%1,%2,%3}, [%4];" : "=r"(v.x), "=r"(v.y), "=r"(v.z), "=r"(v.w) : "l"(p) : "memory"); return v;
}
__device__ __forceinline__ uint2 ld_relaxed2(const uint32_t* p) {
  uint2 v; asm volatile("ld.relaxed.gpu.global.v2.u32 {%0,%1}, [%2];" : "=r"(v.x), "=r"(v.y) : "l"(p) : "memory"); return v;
}
__device__ __forceinline__ void st_relaxed(uint32_t* p, uint32_t v) {
  asm volatile("st.relaxed.gpu.global.u32 [%0], %1;" ::"l"(p), "r"(v) : "memory");
}
__device__ __forceinline__ void st_relaxed2(uint32_t* p, uint32_t a, uint32_t b) {
  asm volatile("st.relaxed.gpu.global.v2.u32 [%0], {%1,%2};" ::"l"(p), "r"(a), "r"(b) : "memory");
}
__device__ __forceinline__ void st_relaxed4(uint32_t* p, uint32_t a, uint32_t b, uint32_t c, uint32_t d) {
  asm volatile("st.relaxed.gpu.global.v4.u32 [%0], {%1,%2,%3,%4};" ::"l"(p), "r"(a), "r"(b), "r"(c), "r"(d) : "memory");
}
__device__ __forceinline__ void st_b128(uint32_t* p, uint32_t a, uint32_t b, uint32_t c, uint32_t d) {
  asm volatile("{ .reg .b64 u, v; .reg .b128 w; mov.b64 u, {%1, %2}; mov.b64 v, {%3, %4}; mov.b128 w, {u, v}; st.relaxed.gpu.global.b128 [%0], w; }"
               ::"l"(p), "r"(a), "r"(b), "r"(c), "r"(d) : "memory");
}
__device__ __forceinline__ uint4 ld_b128(const uint32_t* p) {
  uint4 r;
  asm volatile("{ .reg .b64 u, v; .reg .b128 w; ld.relaxed.gpu.global.b128 w, [%4]; mov.b128 {u, v}, w; mov.b64 {%0, %1}, u; mov.b64 {%2, %3}, v; }"
               : "=r"(r.x), "=r"(r.y), "=r"(r.z), "=r"(r.w) : "l"(p) : "memory");
  return r;
}
__device__ __forceinline__ void st_pairs(uint32_t* p, uint32_t a, uint32_t b, uint32_t tag) {
  asm volatile("{ .reg .b64 u, v; mov.b64 u, {%1, %3}; mov.b64 v, {%2, %3}; st.relaxed.gpu.global.v2.b64 [%0], {u, v}; }"
               ::"l"(p), "r"(a), "r"(b), "r"(tag) : "memory");
}
__device__ __forceinline__ uint4 ld_pairs(const uint32_t* p) {
  uint4 v;
  asm volatile("{ .reg .b64 u, v; ld.relaxed.gpu.global.v2.b64 {u, v}, [%4]; mov.b64 {%0, %1}, u; mov.b64 {%2, %3}, v; }"
               : "=r"(v.x), "=r"(v.y), "=r"(v.z), "=r"(v.w) : "l"(p) : "memory");
  return v;
}
__device__ __forceinline__ uint2 ld_pair(const uint32_t* p) {
  uint2 v;
  asm volatile("{ .reg .b64 u; ld.relaxed.gpu.global.b64 u, [%2]; mov.b64 {%0, %1}, u; }" : "=r"(v.x), "=r"(v.y) : "l"(p) : "memory");
  return v;
}
__device__ __forceinline__ void red_release(uint32_t* p, uint32_t v) {
  asm volatile("red.release.gpu.global.add.u32 [%0], %1;" ::"l"(p), "r"(v) : "memory");
}
__device__ __forceinline__ uint32_t ldg_nc1(const void* p) {
  uint32_t v;
  asm volatile("ld.global.nc.u32 %0, [%1];" : "=r"(v) : "l"(p));
  return v;
}
__device__ __forceinline__ uint4 ldg_nc4(const void* p) {
  uint4 v; asm volatile("ld.global.nc.L1::no_allocate.v4.u32 {%0,%1,%2,%3}, [%4];" : "=r"(v.x), "=r"(v.y), "=r"(v.z), "=r"(v.w) : "l"(p)); return v;
}
__device__ __forceinline__ uint4 ldg_stream4(const void* p) {
  uint4 v;
  asm volatile("ld.global.nc.L1::no_allocate.L2::cache_hint.v4.u32 {%0,%1,%2,%3}, [%4], %5;" : "=r"(v.x), "=r"(v.y), "=r"(v.z), "=r"(v.w) : "l"(p), "l"(l2_stream()));
  return v;
}
__device__ __forceinline__ void stg4(void* p, uint4 v) {
  asm volatile("st.global.v4.u32 [%0], {%1,%2,%3,%4};" ::"l"(p), "r"(v.x), "r"(v.y), "r"(v.z), "r"(v.w) : "memory");
}
__device__ __forceinline__ void wait_counter(const uint32_t* p, uint32_t target) {
  uint32_t n = 0;
  while (__any_sync(0xffffffffu, (int)(ld_acquire(p) - target) < 0)) { watchdog(n); }
}
__device__ __forceinline__ uint32_t tagf(float v, uint32_t tag) { return (__float_as_uint(v) & ~3u) | tag; }
__device__ __forceinline__ bool tag_ok(uint4 v, uint32_t tag) { return (((v.x ^ tag) | (v.y ^ tag) | (v.z ^ tag) | (v.w ^ tag)) & 3u) == 0; }
__device__ __forceinline__ float untag_sum(uint32_t a, uint32_t b) { return __uint_as_float(a & ~3u) + __uint_as_float(b & ~3u); }
__device__ __forceinline__ uint4 poll4(const uint32_t* p, uint32_t tag) {
  uint4 v = ld_relaxed4(p);
  uint32_t n = 0;
  while (!__all_sync(0xffffffffu, tag_ok(v, tag))) { v = ld_relaxed4(p); watchdog(n); }
  return v;
}
__device__ __forceinline__ float bf_lo(uint32_t v) { return __uint_as_float(v << 16); }
__device__ __forceinline__ float bf_hi(uint32_t v) { return __uint_as_float(v & 0xffff0000u); }
__device__ __forceinline__ uint32_t pack_bf(float lo, float hi) {
  uint32_t r; asm("cvt.rn.bf16x2.f32 %0, %1, %2;" : "=r"(r) : "f"(hi), "f"(lo)); return r;
}
__device__ __forceinline__ float rbf(float v) { return __uint_as_float(pack_bf(0.f, v) & 0xffff0000u); }
__device__ __forceinline__ uint32_t hmul2(uint32_t a, uint32_t b) {
  uint32_t r; asm("mul.rn.bf16x2 %0, %1, %2;" : "=r"(r) : "r"(a), "r"(b)); return r;
}
__device__ __forceinline__ uint32_t hadd2(uint32_t a, uint32_t b) {
  uint32_t r; asm("add.rn.bf16x2 %0, %1, %2;" : "=r"(r) : "r"(a), "r"(b)); return r;
}
__device__ __forceinline__ uint32_t hsub2(uint32_t a, uint32_t b) {
  uint32_t r; asm("sub.rn.bf16x2 %0, %1, %2;" : "=r"(r) : "r"(a), "r"(b)); return r;
}
__device__ __forceinline__ uint32_t hmax2(uint32_t a, uint32_t b) {
  uint32_t r; asm("max.bf16x2 %0, %1, %2;" : "=r"(r) : "r"(a), "r"(b)); return r;
}
__device__ __forceinline__ float rcp(float x) { float r; asm("rcp.approx.ftz.f32 %0, %1;" : "=f"(r) : "f"(x)); return r; }
__device__ __forceinline__ float ex2(float x) { float r; asm("ex2.approx.ftz.f32 %0, %1;" : "=f"(r) : "f"(x)); return r; }
__device__ __forceinline__ void stmatrix4(uint32_t addr, uint32_t a, uint32_t b, uint32_t c, uint32_t d) {
  asm volatile("stmatrix.sync.aligned.m8n8.x4.shared.b16 [%0], {%1,%2,%3,%4};" ::"r"(addr), "r"(a), "r"(b), "r"(c), "r"(d) : "memory");
}
__device__ __forceinline__ void ldmatrix4(uint32_t addr, uint32_t& a, uint32_t& b, uint32_t& c, uint32_t& d) {
  asm volatile("ldmatrix.sync.aligned.m8n8.x4.shared.b16 {%0,%1,%2,%3}, [%4];" : "=r"(a), "=r"(b), "=r"(c), "=r"(d) : "r"(addr) : "memory");
}
__device__ __forceinline__ void ldmatrix4t(uint32_t addr, uint32_t& a, uint32_t& b, uint32_t& c, uint32_t& d) {
  asm volatile("ldmatrix.sync.aligned.m8n8.x4.trans.shared.b16 {%0,%1,%2,%3}, [%4];" : "=r"(a), "=r"(b), "=r"(c), "=r"(d) : "r"(addr) : "memory");
}
__device__ __forceinline__ void mma16816(float (&d)[4], uint32_t a0, uint32_t a1, uint32_t a2, uint32_t a3, uint32_t b0, uint32_t b1) {
  asm volatile("mma.sync.aligned.m16n8k16.row.col.f32.bf16.bf16.f32 {%0,%1,%2,%3}, {%4,%5,%6,%7}, {%8,%9}, {%0,%1,%2,%3};"
               : "+f"(d[0]), "+f"(d[1]), "+f"(d[2]), "+f"(d[3]) : "r"(a0), "r"(a1), "r"(a2), "r"(a3), "r"(b0), "r"(b1));
}
__device__ __forceinline__ void sts1(uint32_t a, uint32_t v) { asm volatile("st.shared.u32 [%0], %1;" ::"r"(a), "r"(v) : "memory"); }
__device__ __forceinline__ uint4 lds4(uint32_t a) {
  uint4 v; asm volatile("ld.shared.v4.u32 {%0,%1,%2,%3}, [%4];" : "=r"(v.x), "=r"(v.y), "=r"(v.z), "=r"(v.w) : "r"(a) : "memory"); return v;
}
__device__ __forceinline__ uint2 lds2(uint32_t a) {
  uint2 v; asm volatile("ld.shared.v2.u32 {%0,%1}, [%2];" : "=r"(v.x), "=r"(v.y) : "r"(a) : "memory"); return v;
}
__device__ __forceinline__ uint32_t lds1(uint32_t a) {
  uint32_t v; asm volatile("ld.shared.u32 %0, [%1];" : "=r"(v) : "r"(a) : "memory"); return v;
}
__device__ __forceinline__ void sts2(uint32_t a, uint32_t x, uint32_t y) { asm volatile("st.shared.v2.u32 [%0], {%1,%2};" ::"r"(a), "r"(x), "r"(y) : "memory"); }
__device__ __forceinline__ void sts4(uint32_t a, uint4 v) {
  asm volatile("st.shared.v4.u32 [%0], {%1,%2,%3,%4};" ::"r"(a), "r"(v.x), "r"(v.y), "r"(v.z), "r"(v.w) : "memory");
}
__device__ __forceinline__ float silu_f(float v) { return __fdividef(v, 1.f + __expf(-v)); }
__device__ __forceinline__ uint32_t hfma2(uint32_t a, uint32_t b, uint32_t c) {
  uint32_t r; asm("fma.rn.bf16x2 %0, %1, %2, %3;" : "=r"(r) : "r"(a), "r"(b), "r"(c)); return r;
}
__device__ __forceinline__ void split_inv(float sd, uint32_t& ih, uint32_t& il) {
  const float inv = rcp(sd);
  ih = pack_bf(inv, inv);
  const float lo = inv - bf_lo(ih);
  il = pack_bf(lo, lo);
}
__device__ __forceinline__ uint32_t ln_norm(uint32_t x, uint32_t mean2, uint32_t ih, uint32_t il) {
  const uint32_t d = hsub2(x, mean2);
  return hfma2(d, ih, hmul2(d, il));
}
__device__ __forceinline__ uint32_t modul(uint32_t n, uint32_t c1, uint32_t sh) { return hadd2(hmul2(n, c1), sh); }
__device__ __forceinline__ uint32_t ln_mod(uint32_t x, uint32_t mean2, uint32_t ih, uint32_t il, uint32_t c1, uint32_t sh) {
  return modul(ln_norm(x, mean2, ih, il), c1, sh);
}

#define R8(a, i) "+f"(a[i]), "+f"(a[i + 1]), "+f"(a[i + 2]), "+f"(a[i + 3]), "+f"(a[i + 4]), "+f"(a[i + 5]), "+f"(a[i + 6]), "+f"(a[i + 7])
#define D64 "{%0,%1,%2,%3,%4,%5,%6,%7,%8,%9,%10,%11,%12,%13,%14,%15,%16,%17,%18,%19,%20,%21,%22,%23,%24,%25,%26,%27,%28,%29,%30,%31," \
            "%32,%33,%34,%35,%36,%37,%38,%39,%40,%41,%42,%43,%44,%45,%46,%47,%48,%49,%50,%51,%52,%53,%54,%55,%56,%57,%58,%59,%60,%61,%62,%63}"
template <int TB>
__device__ __forceinline__ void mma_ss(float (&d)[64], uint64_t da, uint64_t db, int sc) {
  asm volatile("{\n.reg .pred p;\nsetp.ne.b32 p, %66, 0;\n"
               "wgmma.mma_async.sync.aligned.m64n128k16.f32.bf16.bf16 " D64 ", %64, %65, p, 1, 1, 0, %67;\n}"
               : R8(d, 0), R8(d, 8), R8(d, 16), R8(d, 24), R8(d, 32), R8(d, 40), R8(d, 48), R8(d, 56)
               : "l"(da), "l"(db), "r"(sc), "n"(TB));
}
template <int TB>
__device__ __forceinline__ void mma_rs(float (&d)[64], uint32_t a0, uint32_t a1, uint32_t a2, uint32_t a3, uint64_t db, int sc) {
  asm volatile("{\n.reg .pred p;\nsetp.ne.b32 p, %69, 0;\n"
               "wgmma.mma_async.sync.aligned.m64n128k16.f32.bf16.bf16 " D64 ", {%64,%65,%66,%67}, %68, p, 1, 1, %70;\n}"
               : R8(d, 0), R8(d, 8), R8(d, 16), R8(d, 24), R8(d, 32), R8(d, 40), R8(d, 48), R8(d, 56)
               : "r"(a0), "r"(a1), "r"(a2), "r"(a3), "l"(db), "r"(sc), "n"(TB));
}
#define D128 "{%0,%1,%2,%3,%4,%5,%6,%7,%8,%9,%10,%11,%12,%13,%14,%15,%16,%17,%18,%19,%20,%21,%22,%23,%24,%25,%26,%27,%28,%29,%30,%31," \
             "%32,%33,%34,%35,%36,%37,%38,%39,%40,%41,%42,%43,%44,%45,%46,%47,%48,%49,%50,%51,%52,%53,%54,%55,%56,%57,%58,%59,%60,%61,%62,%63," \
             "%64,%65,%66,%67,%68,%69,%70,%71,%72,%73,%74,%75,%76,%77,%78,%79,%80,%81,%82,%83,%84,%85,%86,%87,%88,%89,%90,%91,%92,%93,%94,%95," \
             "%96,%97,%98,%99,%100,%101,%102,%103,%104,%105,%106,%107,%108,%109,%110,%111,%112,%113,%114,%115,%116,%117,%118,%119,%120,%121,%122,%123,%124,%125,%126,%127}"
#define R128(d, e) R8(d, 0), R8(d, 8), R8(d, 16), R8(d, 24), R8(d, 32), R8(d, 40), R8(d, 48), R8(d, 56), \
                   R8(e, 0), R8(e, 8), R8(e, 16), R8(e, 24), R8(e, 32), R8(e, 40), R8(e, 48), R8(e, 56)
__device__ __forceinline__ void mma256_ss(float (&d)[64], float (&e)[64], uint64_t da, uint64_t db, int sc) {
  asm volatile("{\n.reg .pred p;\nsetp.ne.b32 p, %130, 0;\n"
               "wgmma.mma_async.sync.aligned.m64n256k16.f32.bf16.bf16 " D128 ", %128, %129, p, 1, 1, 0, 1;\n}"
               : R128(d, e) : "l"(da), "l"(db), "r"(sc));
}
__device__ __forceinline__ void mma256_rs(float (&d)[64], float (&e)[64], uint32_t a0, uint32_t a1, uint32_t a2, uint32_t a3, uint64_t db) {
  asm volatile("{\n.reg .pred p;\nsetp.ne.b32 p, 1, 0;\n"
               "wgmma.mma_async.sync.aligned.m64n256k16.f32.bf16.bf16 " D128 ", {%128,%129,%130,%131}, %132, p, 1, 1, 1;\n}"
               : R128(d, e) : "r"(a0), "r"(a1), "r"(a2), "r"(a3), "l"(db));
}
template <int N> __device__ __forceinline__ void keep(float (&a)[N]) {
#pragma unroll
  for (int i = 0; i < N; i++) asm volatile("" : "+f"(a[i])::"memory");
}
template <int N> __device__ __forceinline__ void keep(uint32_t (&a)[N]) {
#pragma unroll
  for (int i = 0; i < N; i++) asm volatile("" : "+r"(a[i])::"memory");
}

#define STAMP(idx) do {} while (0)
#define PROF(grp, cond, idx) do {} while (0)

constexpr float SCL2 = 1.4426950408889634f * 0.08838834764831845f;

__device__ __forceinline__ void pack_p(const float (&s)[64], uint32_t (&p)[32]) {
#pragma unroll
  for (int i = 0; i < 32; i++) p[i] = pack_bf(s[2 * i], s[2 * i + 1]);
}

__device__ __forceinline__ void issue_qk(float (&s)[64], uint32_t q0, uint32_t q1, uint32_t kslot) {
  const uint64_t db = make_desc(kslot, 16, 1024), da0 = make_desc(q0, 16, 1024), da1 = make_desc(q1, 16, 1024);
#pragma unroll
  for (int kk = 0; kk < 8; kk++) mma_ss<0>(s, (kk < 4 ? da0 : da1) + (kk & 3) * 2, db + (kk >> 2) * 1024 + (kk & 3) * 2, kk != 0);
}
__device__ __forceinline__ void issue_pv(float (&o)[64], uint32_t (&p)[32], uint32_t vslot, int acc) {
  uint64_t db = make_desc(vslot, 16384, 1024);
#pragma unroll
  for (int kk = 0; kk < 8; kk++)
    mma_rs<1>(o, p[4 * kk], p[4 * kk + 1], p[4 * kk + 2], p[4 * kk + 3], db + kk * 128, kk == 0 ? acc : 1);
}

template <int H>
__device__ __forceinline__ void store_chunk(const float (&a)[64], uint32_t addr) {
#pragma unroll
  for (int i = 8 * H; i < 8 * H + 8; i += 2)
    stmatrix4(addr ^ ((i & 7) << 4), pack_bf(a[4 * i], a[4 * i + 1]), pack_bf(a[4 * i + 2], a[4 * i + 3]),
              pack_bf(a[4 * i + 4], a[4 * i + 5]), pack_bf(a[4 * i + 6], a[4 * i + 7]));
}
template <int H>
__device__ __forceinline__ void store_chunk(const float (&a)[64], float i0, float i1, uint32_t addr) {
#pragma unroll
  for (int i = 8 * H; i < 8 * H + 8; i += 2)
    stmatrix4(addr ^ ((i & 7) << 4), pack_bf(a[4 * i] * i0, a[4 * i + 1] * i0), pack_bf(a[4 * i + 2] * i1, a[4 * i + 3] * i1),
              pack_bf(a[4 * i + 4] * i0, a[4 * i + 5] * i0), pack_bf(a[4 * i + 6] * i1, a[4 * i + 7] * i1));
}
__device__ __forceinline__ float inv_quad_sum(float l) {
  l += __shfl_xor_sync(0xffffffffu, l, 1);
  l += __shfl_xor_sync(0xffffffffu, l, 2);
  return rcp(l);
}

__device__ __forceinline__ void write_table(uint32_t table, bool ca, uint32_t t, const uint4& m0, const uint4& m1) {
  float c0 = untag_sum(m0.x, m1.x), c1 = untag_sum(m0.y, m1.y), c2 = untag_sum(m0.z, m1.z), c3 = untag_sum(m0.w, m1.w);
  if (ca) { c0 = 1.f + rbf(c0); c1 = 1.f + rbf(c1); c2 = 1.f + rbf(c2); c3 = 1.f + rbf(c3); }
  const uint32_t d = table + (t >> 2) * 64 + (t & 1) * 32 + (t & 2) * 2 + (ca ? 0 : 8);
  sts1(d, pack_bf(c0, c1));
  sts1(d + 16, pack_bf(c2, c3));
}

__device__ __forceinline__ void ln_scalars(float mean, float var, float& mb, float& sd) {
  mb = rbf(mean);
  float r; asm("sqrt.approx.ftz.f32 %0, %1;" : "=f"(r) : "f"(rbf(rbf(var) + 1e-5f)));
  sd = rbf(r);
}

__global__ void __cluster_dims__(2, 1, 1) __launch_bounds__(384, 1) fused_kernel(const __grid_constant__ Maps maps, const Ptrs P) {
  extern __shared__ __align__(1024) uint8_t smem_raw[];
  const uint32_t base = smem_u32(smem_raw);
  const int tid = threadIdx.x, lane = tid & 31;
  const int warp = __shfl_sync(0xffffffffu, tid >> 5, 0);
  const int b = blockIdx.x;
  PROF(31, tid == 0, 0);

  if (b >= NMAIN) {
    float* sc = reinterpret_cast<float*>(smem_raw);
    float* red = sc + DM;
    for (int k = tid; k < DM; k += 384) sc[k] = rbf(silu_f(__bfloat162float(P.c[k])));
    __syncthreads();
    if (tid < 256) {
      const int col = 2048 + (b - NMAIN) * 1024 + (tid & 127) * 8, r0 = (tid >> 7) * 512;
      float acc[8];
#pragma unroll
      for (int e = 0; e < 8; e++) acc[e] = 0.f;
#pragma unroll 1
      for (int r = r0; r < r0 + 512; r += HU) {
        uint4 w[HU];
#pragma unroll
        for (int u = 0; u < HU; u++) w[u] = ldg_stream4(P.w_mod + (size_t)(r + u) * NMOD + col);
#pragma unroll
        for (int u = 0; u < HU; u++) {
          float s = sc[r + u];
          acc[0] += s * bf_lo(w[u].x); acc[1] += s * bf_hi(w[u].x); acc[2] += s * bf_lo(w[u].y); acc[3] += s * bf_hi(w[u].y);
          acc[4] += s * bf_lo(w[u].z); acc[5] += s * bf_hi(w[u].z); acc[6] += s * bf_lo(w[u].w); acc[7] += s * bf_hi(w[u].w);
        }
      }
      if (tid >= 128) {
#pragma unroll
        for (int e = 0; e < 8; e++) red[(tid & 127) * 8 + e] = acc[e];
      }
      const uint32_t tag = ld_relaxed(&g_epoch) % 3 + 1;
      bar_sync(1, 256);
      if (tid < 128) {
        uint32_t o[8];
#pragma unroll
        for (int e = 0; e < 8; e++) o[e] = __float_as_uint(rbf(acc[e] + red[tid * 8 + e])) | tag;
        st_relaxed4(g_mod + col, o[0], o[1], o[2], o[3]);
        st_relaxed4(g_mod + col + 4, o[4], o[5], o[6], o[7]);
        const uint4 wr = ldg_nc4(P.w_r + tid * 8);
        const uint32_t wv[4] = {wr.x, wr.y, wr.z, wr.w};
        float dsum = 0.f;
#pragma unroll
        for (int e = 0; e < 8; e++) {
          const float m = bf_hi(o[e]);
          dsum += (b == NMAIN + 2 ? rbf(1.f + m) : m) * ((e & 1) ? bf_hi(wv[e >> 1]) : bf_lo(wv[e >> 1]));
        }
#pragma unroll
        for (int k = 16; k > 0; k >>= 1) dsum += __shfl_xor_sync(0xffffffffu, dsum, k);
        if (lane == 0) st_relaxed(g_mod + (b - NMAIN) * 4 + warp, tagf(dsum, tag));
      }
    }
    PROF(2, tid == 0, 1);
    return;
  }

  const int rank = b & 1;
  const int rb = ((b >> 4) << 1) | rank, cj = (b >> 1) & 7;
  const bool late = b & 4;
  const uint32_t bfull = base + OFF_BAR, bempty = bfull + NSLOT * 8;
  const uint32_t gfull = bempty + NSLOT * 8, gempty = gfull + 32;
  const uint32_t bar_ofull = gempty + 32;
  const uint32_t bar_ofree = bar_ofull + 32;
  const uint32_t bar_par = bar_ofree + 32;
  const uint32_t bar_mod = bar_par + 8;
  const uint32_t bar_pread = bar_mod + 8;
  const uint32_t bar_xres = bar_pread + 8;
  const uint32_t bar_ring = bar_xres + 8;
  const uint32_t bar_box = bar_ring + 24;
  const uint32_t bar_go = bar_box + 96;
  const uint32_t bar_go2 = bar_go + 16;
  const uint32_t bar_cnt = bar_go + 24;
  const uint32_t xfull = bar_go + 40, xempty = xfull + 32;
  const uint32_t bar_hw = xempty + 32, bar_hx = bar_hw + 8;
  const uint32_t bar_hpub = bar_hx + 16;
  const uint32_t bar_win = bar_hpub + 16;
  const uint32_t bar_rx = bar_win + 8;
  const uint32_t bar_sel = bar_rx + 8;
  const uint32_t bar_gate = bar_sel + 8;
  const uint32_t bar_rel = bar_gate + 8;
  const uint32_t bar_od = bar_rel + 8;
  const uint32_t bar_mod2 = bar_od + 8;
  const uint32_t bar_res = bar_go + 8;
  const uint32_t stage = base + OFF_STAGE, par = base + OFF_PAR;

  if (warp == 10 && elect_one()) prefetch_map(&maps.wm);
  if (warp == 8 && elect_one()) {
    for (int s = 0; s < NSLOT; s++) { mbar_init(bfull + s * 8, 1); mbar_init(bempty + s * 8, 16); }
    for (int s = 0; s < 4; s++) { mbar_init(gfull + s * 8, 1); mbar_init(gempty + s * 8, 16); mbar_init(xfull + s * 8, 1); mbar_init(xempty + s * 8, 8); mbar_init(bar_ofree + s * 8, 1); mbar_init(bar_ofull + s * 8, 128); }
    mbar_init(bar_par, 64); mbar_init(bar_mod, 256); mbar_init(bar_pread, 2); mbar_init(bar_xres, 1);
    mbar_init(bar_ring, 8); mbar_init(bar_ring + 8, 8); mbar_init(bar_ring + 16, 8);
    mbar_init(bar_go, 1); mbar_init(bar_go2, 1); mbar_init(bar_cnt, 1); mbar_init(bar_cnt + 8, 1); mbar_init(bar_hpub, 8); mbar_init(bar_hpub + 8, 8); mbar_init(bar_res, 1); mbar_init(bar_win, 1); mbar_init(bar_rx, 1); mbar_init(bar_sel, 64); mbar_init(bar_gate, 8); mbar_init(bar_rel, 8); mbar_init(bar_od, 1); mbar_init(bar_mod2, 64);
    for (int s = 0; s < 12; s++) mbar_init(bar_box + s * 8, 1);
    asm volatile("fence.mbarrier_init.release.cluster;" ::: "memory");
    prefetch_map(&maps.x); prefetch_map(&maps.wq); prefetch_map(&maps.k); prefetch_map(&maps.v);
  }
  if (warp == 9 && elect_one()) {
    mbar_init(bar_hw, 1); mbar_init(bar_hx, 1); mbar_init(bar_hx + 8, 1);
    asm volatile("fence.mbarrier_init.release.cluster;" ::: "memory");
    mbar_expect_tx(bar_hw, 32768);
    mbar_expect_tx(bar_hx, 16384);
    mbar_expect_tx(bar_hx + 8, 16384);
    const __nv_bfloat16* xs = P.x + (size_t)(rb * 128 + cj * 16) * DM;
    bulk_load(base + 2 * GST_BYTES, xs, 16384, bar_hx);
    if (!late) {
      tma2d(stage, &maps.wm, (b >> 1) * 32, rank * 512, bar_hw);
      tma2d(stage + 16384, &maps.wm, (b >> 1) * 32, rank * 512 + 256, bar_hw);
    }
    bulk_load(base + 3 * GST_BYTES, xs + 8 * DM, 16384, bar_hx + 8);
  }
  cluster_arrive();

  if (warp >= 8) {
    asm volatile("setmaxnreg.dec.sync.aligned.u32 40;");
    if (warp < 10) bar_arrive(1, 320);
    const uint32_t epoch = ld_relaxed(&g_epoch);
    cluster_wait();
    if (warp == 8) {
      const int kvrow = (cj >> 1) * SK + (SK - WIN);
      int wch = cj * 8 + rank * 2;
#pragma unroll 1
      for (int ps = 0; ps < 3; ps++) {
        const CUtensorMap* mw = ps == 2 ? &maps.wo : &maps.wq;
        const uint32_t xt = ps == 1 ? XT1 : XT2, wt = ps == 0 ? WT0 : (ps == 1 ? WT1 : WT2);
        const int nst = ps == 2 ? 32 : 16;
#pragma unroll 1
        for (int i = 0; i < nst; i++) {
          const uint32_t bf = gfull + (i & 3) * 8;
          const int kt = ps == 2 ? (((cj & 1) * 4 + ((i >> 1) & 3)) * 4 + (i >> 3)) * 2 + (i & 1) : (ps ? i : slice_of(i) + (b & 14)) & 15;
          const uint32_t wd = base + unit_of(wt, i & 3) + rank * UNIT, xd = base + unit_of(xt, i & 3);
          const uint8_t* xs = g_act + (uint32_t)(rb * 80 + (ps - 1) * 16 + kt) * UNIT;
          if (ps == 0 && i == HD) mbar_wait(bar_mod, 0);
          const bool xfirst = ps && i < 2;
          if (ps == 2 && i == 0) mbar_wait(bar_ofree + 24, 0);
          if (i == 0) fence_async();
          mbar_wait(gempty + (i & 3) * 8, ((i >> 2) & 1) ^ 1);
          if (elect_one()) {
            mbar_expect_tx(bf, ps && i != 1 ? (i ? GST_BYTES : 4 * UNIT) : 2 * UNIT);
            if (ps && i == 0) bulk_load_stream(xd, xs, 2 * UNIT, bf);
          }
          if (ps && i < 4) mbar_wait(bempty + i * 8, 1);
          if (elect_one()) {
            if (!xfirst || i == rank) tma3d_mc<true>(wd, mw, 0, (i == 31 ? kt ^ (rank * 32) : kt) * 64, i == 31 ? cj * 2 : wch, bf);
            if (xfirst && i == rank) tma3d_mc<true>(wd + (i ? -UNIT : UNIT), mw, 0, (kt ^ 1) * 64, wch, bf);
          }
          if (ps) {
            if (i == 16 || i == 24) { mbar_wait(bar_cnt + i - 16, 0); fence_async(); }
            if (i == RES0) mbar_wait(bar_res, 0);
            if (i == 2) mbar_wait(bar_ofree + (ps - 1) * 16, 0);
            if (elect_one()) {
              if (i == 31) bulk_load(xd, xs, UNIT, bf); else if (!xfirst) bulk_load_stream(xd, xs, UNIT, bf);
              mbar_arrive_pred(bar_go, i == GOST - 1);
              if (PG0 < 16) mbar_arrive_pred(bar_go2, ps == 1 && i == PG0);
              mbar_arrive_pred(bar_od, i == (ps == 1 ? ODS1 : ODS));
              if (i == RES0) mbar_expect_tx(bar_xres, 32768);
              if (i == RES0 || i == RES1) tma2d(base + OFF_RES + (i == RES1) * UNIT, &maps.x, cj * 128 + (i == RES1) * 64, rb * 128, bar_xres);
            }
          }
        }
        if (ps == 2) break;
        wch = ps ? ((wch >> 3) ^ rank) * 2 : wch + 4;
#pragma unroll 1
        for (int u = 0; u < 16; u++) {
          const bool isk = (u == 0) || ((u & 1) && u < 15);
          const int blk = (isk ? (u + 1) >> 1 : (u == 15 ? 7 : (u >> 1) - 1)) & 3;
          const uint32_t sl = base + unit_of(ps ? AT1 : AT0, u & 3) + rank * UNIT, bf = bfull + (u & 3) * 8;
          if (u < 4) mbar_wait(gempty + ((u + 1) >> 1) * 8, 1);
          mbar_wait(bempty + (u & 3) * 8, ((u >> 2) & 1) ^ 1);
          if (elect_one()) {
            mbar_arrive_pred(bar_go2, ps && u + 16 == PG0);
            mbar_expect_tx(bf, SLOT_BYTES);
            tma3d_mc<false>(sl, isk ? &maps.k : &maps.v, 0, kvrow + blk * 128, rank, bf);
          }
        }
      }
      if (elect_one()) mbar_expect_tx(bar_rx, UNIT);
      mbar_wait(bar_rel, 0);
      if (elect_one()) {
        bulk_load_stream(base + UNIT, g_act + (uint32_t)(rb * 80 + 16 + 63 - (cj & 1) * 32) * UNIT, UNIT, bar_rx);
      }
      if (b < NFFN) {
#pragma unroll 1
        for (int u = 0; u < 12; u++) {
          const uint32_t dst = base + unit_of(u < 4 ? FT_G : (u < 8 ? FT_U : FT_D), u & 3);
          if (elect_one()) mbar_expect_tx(bar_box + u * 8, UNIT);
          if (u == FB0 || u == FB1 || u == FB2) mbar_wait(bar_ring + (u == FB2 ? 16 : u == FB1 ? 8 : 0), 0);
          const int fp = u < FPB ? FPACE0 : FPACE;
          if (u >= fp) mbar_wait(bar_box + (u - fp) * 8, 0);
          if (elect_one()) {
            if (u < 8) tma2d(dst, u < 4 ? &maps.wg : &maps.wu, b * 32, (u & 3) * 256, bar_box + u * 8);
            else tma3d(dst, &maps.wd, 0, b * 32, (u - 8) * 4, bar_box + u * 8);
          }
        }
      }
    } else if (warp == 9) {
      const uint32_t target = 8 * (epoch + 1);
      uint32_t hmask = 0;
#pragma unroll 1
      for (int i = 0; i < 16; i++) {
        if (i == HDX) mbar_wait(bar_mod, 0);
        const int kt = (2 * cj + slice_of(i)) & 15;
        const uint32_t need = i == 15 ? 0xffffu : 1u << kt;
        if (i >= NRS && (hmask & need) != need) {
          uint32_t n = 0;
          do { hmask = __ballot_sync(0xffffffffu, ld_acquire(&g_cnt_h[rb * 32 + (lane & 15)]) == epoch + 1); watchdog(n); } while ((hmask & need) != need);
          PROF(1, lane == 0 && i == NRS, 26);
          fence_async();
        }
        mbar_wait(xempty + (i & 3) * 8, ((i >> 2) & 1) ^ 1);
        if (elect_one()) {
          mbar_expect_tx(xfull + (i & 3) * 8, UNIT);
          if (i < NRS) tma2d(base + (i & 3) * GST_BYTES, &maps.x, kt * 64, rb * 128, xfull + (i & 3) * 8);
          else bulk_load_stream(base + (i & 3) * GST_BYTES, g_act + (uint32_t)(rb * 80 + kt) * UNIT, UNIT, xfull + (i & 3) * 8);
        }
      }
      prefetch_map(&maps.wo);
#pragma unroll 1
      for (int t = 0; t < 4; t++) {
        if (t & 1) mbar_wait(bar_od, t >> 1);
#pragma unroll 1
        for (int p = 0; p < 32768 / OPS; p++) {
          const uint32_t w = p / (16384 / OPS), c = (p / (8192 / OPS)) & 1, off = w * 8192 + (p % (8192 / OPS)) * OPS;
          mbar_wait(bar_ofull + (t & 1) * 16 + w * 8, t >> 1);
          if (elect_one()) {
            bulk_store(g_act + (uint32_t)(rb * 80 + 16 + (cj * 4 + t) * 2 + c) * UNIT + off, base + unit_of(QT, 2 * t + c) + off, OPS);
            asm volatile("cp.async.bulk.commit_group;" ::: "memory");
            asm volatile("cp.async.bulk.wait_group.read %0;" ::"n"(OFL) : "memory");
          }
        }
        if (elect_one()) {
          asm volatile("cp.async.bulk.wait_group.read 0;" ::: "memory");
          mbar_arrive(t < 3 ? bar_ofree + t * 8 : bar_res);
          asm volatile("cp.async.bulk.wait_group 0;" ::: "memory");
          fence_async();
          red_release(&g_cnt_o[((rb * 4 + t) * 2 + (cj >> 2)) * 32], 2);
        }
        if (t) {
          wait_counter(&g_cnt_o[(rb * 8 + 2 * t + (cj & 1)) * 32], target);
          if (t & 1) wait_counter(&g_cnt_o[(rb * 8 + (t == 1 ? cj & 1 : 7 - (cj & 1))) * 32], target);
          if (elect_one()) mbar_arrive(t == 1 ? bar_ofree + 24 : bar_cnt + t * 8 - 16);
        }
      }
      PROF(2, lane == 0, 27);
      const uint32_t tag = epoch % 3 + 1;
      const uint32_t* inbox = g_cand + (b >> 1) % CR * 512 + (lane & 15) * CS;
      mbar_wait(bar_ring + 16, 0);
      uint32_t c0 = ld_relaxed(inbox), n = 0;
#define CAND_STEP(cv)                                                                                        \
      {                                                                                                      \
        const bool valid = (cv & 3u) == tag, all = __all_sync(0xffffffffu, valid);                           \
        const uint32_t best = __reduce_max_sync(0xffffffffu, valid ? cv : 0u);                               \
        const uint32_t blk = __ffs(__ballot_sync(0xffffffffu, cv == best)) - 1;                              \
        if (best) sts2(par + PAR_CONST + 56, best, (blk << 7 | (~best >> 2 & 127)) | (all ? 0x1800 : 0x800)); \
        if (all) break;                                                                                      \
        cv = ld_relaxed(inbox);                                                                              \
      }
      while (true) { CAND_STEP(c0) watchdog(n); }
    } else {
      const int t2 = tid - 320;
      if (late && warp == 10) {
        mbar_wait(bar_hx, 0);
        if (elect_one()) {
          tma2d(stage, &maps.wm, (b >> 1) * 32, rank * 512, bar_hw);
          tma2d(stage + 16384, &maps.wm, (b >> 1) * 32, rank * 512 + 256, bar_hw);
        }
      }
      {
        const uint32_t tag = epoch % 3 + 1;
        mbar_wait(bar_hx + 8, 0);
        mbar_wait(bar_hw, 0);
        __nanosleep(late ? OSL2 : OSL);
        {
          const uint32_t t7 = (warp & 1) * 64 + (lane >> 4) * 32 + 16 + (lane & 15);
          const uint32_t* pm = g_modp + ((cj * 128 + t7 * 4) & (DM - 1));
          uint4 m0, m1, m2, m3;
          uint32_t n = 0;
          do {
            m0 = ld_relaxed4(pm); m1 = ld_relaxed4(pm + 2 * DM); m2 = ld_relaxed4(pm + DM); m3 = ld_relaxed4(pm + 3 * DM);
            watchdog(n);
          } while (!__all_sync(0xffffffffu, tag_ok(m0, tag) && tag_ok(m1, tag) && tag_ok(m2, tag) && tag_ok(m3, tag)));
          write_table(par, false, t7, m0, m1);
          write_table(par, true, t7, m2, m3);
          mbar_arrive(bar_mod2);
        }
      }
      mbar_wait(bar_hpub + (warp & 1) * 8, 0);
      PROF(1, t2 == 0, 24);
#pragma unroll 1
      for (int c = 0; c < 8; c++) {
        const uint32_t off = (warp & 1) * UNIT + c * 2048 + lane * 16;
        uint8_t* dst = g_act + (uint32_t)(rb * 80 + cj * 2) * UNIT + off;
        const uint4 v0 = lds4(stage + off), v1 = lds4(stage + off + 512), v2 = lds4(stage + off + 1024), v3 = lds4(stage + off + 1536);
        stg4(dst, v0); stg4(dst + 512, v1); stg4(dst + 1024, v2); stg4(dst + 1536, v3);
      }
      __syncwarp();
      PROF(1, t2 == 0, 15);
      if (lane == 0) {
        mbar_arrive(bar_pread);
        red_release(&g_cnt_h[rb * 32 + cj * 2 + (warp & 1)], 1);
        PROF(1, t2 == 0, 25);
        prefetch_map(&maps.wg); prefetch_map(&maps.wu); prefetch_map(&maps.wd); prefetch_map(&maps.out);
      }
      __syncwarp();
      if (b < NFFN) {
        mbar_wait(bar_go2, 0);
        const __nv_bfloat16* pg = ((b & 1) ? P.w_up : P.w_gate) + (b >> 1) * 64 + (size_t)t2 * FF;
        const __nv_bfloat16* pd = P.w_down + (size_t)b * 32768 + t2 * 64;
        PROF(2, t2 == 0, 13);
#pragma unroll 1
        for (int i = 0; i < WN; i += WB) {
          uint32_t v[WB];
#pragma unroll
          for (int u = 0; u < WB; u++) {
            const int k = i + u;
            asm volatile("ld.global.cg.L2::128B.u32 %0, [%1];" : "=r"(v[u]) : "l"(k < 16 ? pg + (size_t)k * 64 * FF : pd + (k - 16) * 4096));
          }
#pragma unroll
          for (int u = 1; u < WB; u++) v[0] ^= v[u];
          sts1(par + PAR_SINK + t2 * 4, v[0]);
        }
        PROF(2, t2 == 0, 14);
      }
      const uint32_t tag = epoch % 3 + 1;
      mbar_wait(bar_go, 0);
      bar_sync(4, 64);
      if (warp == 10) {
        const uint32_t* src = g_mod + 2 * DM + cj * 128 + lane * 4;
        const uint2 wr = *reinterpret_cast<const uint2*>(P.w_r + cj * 128 + lane * 4);
        uint4 vga, vsb, vcb, vgb;
        uint32_t n = 0;
        do {
          vga = ld_relaxed4(src); vsb = ld_relaxed4(src + DM); vcb = ld_relaxed4(src + 2 * DM); vgb = ld_relaxed4(src + 3 * DM);
          watchdog(n);
        } while (!__all_sync(0xffffffffu, tag_ok(vga, tag) && tag_ok(vsb, tag) && tag_ok(vcb, tag) && tag_ok(vgb, tag)));
        const float c0 = rbf(1.f + bf_hi(vcb.x)), c1 = rbf(1.f + bf_hi(vcb.y)), c2 = rbf(1.f + bf_hi(vcb.z)), c3 = rbf(1.f + bf_hi(vcb.w));
        const float a0 = c0 * bf_lo(wr.x), a1 = c1 * bf_hi(wr.x), a2 = c2 * bf_lo(wr.y), a3 = c3 * bf_hi(wr.y);
        const uint32_t h0 = pack_bf(a0, a1), h1 = pack_bf(a2, a3);
        const uint32_t t1 = par + PAR_T1 + (lane >> 2) * 64 + (lane & 1) * 32 + (lane & 2) * 2;
        sts1(t1, h0); sts1(t1 + 8, pack_bf(a0 - bf_lo(h0), a1 - bf_hi(h0)));
        sts1(t1 + 16, h1); sts1(t1 + 24, pack_bf(a2 - bf_lo(h1), a3 - bf_hi(h1)));
        const uint32_t tg = par + PAR_SINK + (lane >> 3) * 64 + (lane & 1) * 32 + (lane & 6) * 2;
        sts1(tg, __byte_perm(vga.x, vga.y, 0x7632)); sts1(tg + 16, __byte_perm(vga.z, vga.w, 0x7632));
        sts4(par + PAR_T2 + lane * 32, make_uint4(pack_bf(c0, c1), __byte_perm(vsb.x, vsb.y, 0x7632), __byte_perm(vgb.x, vgb.y, 0x7632), __byte_perm(vga.x, vga.y, 0x7632)));
        sts4(par + PAR_T2 + lane * 32 + 16, make_uint4(pack_bf(c2, c3), __byte_perm(vsb.z, vsb.w, 0x7632), __byte_perm(vgb.z, vgb.w, 0x7632), __byte_perm(vga.z, vga.w, 0x7632)));
      } else {
        const uint4 g = poll4((lane & 8) ? g_mod + 8 - (lane & 1) * 4 : g_mod + 5 * DM + (b >> 4) * 128 + (lane & 7) * 16 + (b & 12), tag);
        sts1(par + PAR_CONST + 60, 0);
        if (lane < 8) sts1(par + PAR_CONST + 16 + lane * 4, (b & 2) ? ((b & 1) ? g.w : g.z) : ((b & 1) ? g.y : g.x));
        else if (lane < 10) sts2(par + PAR_CONST + (lane - 8) * 8, __float_as_uint(untag_sum(g.x, g.y) + untag_sum(g.z, g.w)), epoch);
      }
      __syncwarp();
#pragma unroll 4
      for (int q = 0; q < 32; q++) st_b128(g_xch + ((size_t)b * 8 * 256 + q * 64 + t2) * 4, (epoch & 1) << 16, 0, 0, 0);
      for (int q = 0; q < 2; q++) st_relaxed4(g_stats + ((size_t)cj * SEQ + rb * 128 + q * 64 + t2) * 4, 0, 0, 0, 0);
      if (b < NFFN)
        for (int q = 0; q < 2; q++) st_relaxed4(ypart_slot(b, q * 64 + t2), 0, 0, 0, 0);
      st_relaxed4(g_row + rb * 2 * DM + (t2 >> 5) * DM + cj * 128 + (t2 & 31) * 4, 0, 0, 0, 0);
      __threadfence();
      mbar_arrive(bar_par);
      mbar_wait(bar_gate, 0);
      uint32_t have = 0, n = 0;
      while (true) {
        const uint32_t st = lds1(par + PAR_CONST + 60) >> 7;
        if ((st & 31) != have) {
          const uint32_t* hsrc = g_row + (st & 15) * 2 * DM + t2 * 4;
          uint4 hv[4];
          bool ok = true;
#pragma unroll
          for (int i = 0; i < 4; i++) hv[i] = ld_pairs(hsrc + i * 256);
#pragma unroll
          for (int i = 0; i < 4; i++) {
            sts2(base + ((FT_G >> i * 4) & 15) * UNIT + (warp & 1) * 8192 + 256 + lane * 8, hv[i].x, hv[i].z);
            ok = ok && hv[i].y == tag && hv[i].w == tag;
          }
          have = __all_sync(0xffffffffu, ok) ? st & 31 : 0;
        }
        if ((st ^ have) == 32) break;
        watchdog(n);
      }
      mbar_arrive(bar_sel);
    }
    __syncwarp();
    cluster_arrive();
    {
      const uint32_t tag = epoch % 3 + 1, t3 = tid - 256;
      mbar_wait(bar_win, 0);
      uint2 win = lds2(par + PAR_CONST + 56);
      win.y &= 0x7ff;
      const uint32_t* fsrc = g_row + (win.y >> 7) * 2 * DM + (b >> 4) * 128 + (t3 & 7) * 16 + (b & 6) * 2 + ((b >> 2) & 2);
      const uint32_t* ysrc = ypart_slot(min(t3, NFFN - 1), b);
      uint2 fh = ld_pair(fsrc), fx = ld_pair(fsrc + DM);
      uint4 ya = ld_b128(ysrc);
      const float rwin = __uint_as_float(((int)win.x < 0 ? win.x & 0x7fffffffu : ~win.x) & ~0x1ffu);
      const float rs = rbf(rcp(1.f + __expf(-rbf(rwin))));
      uint32_t n = 0;
      while (__any_sync(0xffffffffu, fh.y != tag || fx.y != tag)) { fh = ld_pair(fsrc); fx = ld_pair(fsrc + DM); watchdog(n); }
      while (true) {
        const bool miss = ((ya.x & 1) | (ya.y & 1) << 1) != tag;
        if (!__any_sync(0xffffffffu, miss)) break;
        if (miss) ya = ld_b128(ysrc);
        watchdog(n);
      }
      PROF(8, t3 == 0, 5);
      float y[8] = {bf_lo(ya.x & ~1u), bf_hi(ya.x), bf_lo(ya.y & ~1u), bf_hi(ya.y), bf_lo(ya.z), bf_hi(ya.z), bf_lo(ya.w), bf_hi(ya.w)};
#pragma unroll
      for (int h = 4; h > 0; h >>= 1) {
        const bool up = lane & (h * 2);
#pragma unroll
        for (int e = 0; e < h; e++) y[e] = (up ? y[e + h] : y[e]) + __shfl_xor_sync(0xffffffffu, up ? y[e] : y[e + h], h * 2);
      }
      y[0] += __shfl_xor_sync(0xffffffffu, y[0], 1);
      if (!(lane & 1)) sts1(par + PAR_RED + 64 + t3 * 2, __float_as_uint(y[0]));
      bar_sync(4, 128);
      if (t3 < 8) {
        float y0 = 0.f;
#pragma unroll
        for (int w7 = 0; w7 < 7; w7++) y0 += __uint_as_float(lds1(par + PAR_RED + 64 + w7 * 32 + t3 * 4));
        const uint32_t gv = lds1(par + PAR_CONST + 16 + t3 * 4);
        const uint32_t upd = hmul2(pack_bf(y0, y0), pack_bf(rs, rs));
        const uint32_t r = hadd2(fx.x, hmul2(__byte_perm(gv, gv, 0x3232), hadd2(fh.x, upd)));
        reinterpret_cast<uint16_t*>(P.out)[(size_t)win.y * DM + (b >> 4) * 128 + t3 * 16 + (b & 15)] = (b & 1) ? r >> 16 : r;
        if (b == 0 && t3 == 0) st_relaxed(&g_epoch, epoch + 1);
      }
      PROF(31, t3 == 0, 36);
    }
    cluster_wait();
  } else {
    const int wg = warp >> 2;

    uint32_t tag;
    {
      uint32_t* const pmod = g_modp + rank * 2 * DM + (b >> 1) * 32 + lane;
      uint32_t* const pln = g_ln1 + (rb * 128 + cj * 16 + warp) * 4;
      uint32_t sc[8];
#pragma unroll
      for (int k = 0; k < 8; k++) sc[k] = ldg_nc1(P.c + rank * 512 + warp * 64 + k * 8 + (lane & 3) * 2);
      const uint32_t epoch = ld_relaxed(&g_epoch);
      if (warp == 0) st_relaxed(pmod, 0);
      if (lane == 0) { st_b128(pln, 0, 0, 0, 0); st_b128(pln + 32, 0, 0, 0, 0); }
      asm volatile("setmaxnreg.inc.sync.aligned.u32 232;");
      bar_sync(1, 320);
#pragma unroll
      for (int k = 0; k < 8; k++) sc[k] = pack_bf(silu_f(bf_lo(sc[k])), silu_f(bf_hi(sc[k])));
      keep(sc);
      tag = epoch % 3 + 1;
#pragma unroll
      for (int part = 0; part < 4; part++) {
        if (!(part & 1)) {
          const uint32_t xa = base + (2 + part / 2) * GST_BYTES + warp * 2048 + lane * 16;
          mbar_wait(bar_hx + part * 4, 0);
          float s0 = 0.f, s1 = 0.f, q0 = 0.f, q1 = 0.f;
#pragma unroll
          for (int q = 0; q < 4; q++) {
            const uint4 xv = lds4(xa + q * 512);
            const uint32_t u[4] = {xv.x, xv.y, xv.z, xv.w};
#pragma unroll
            for (int e = 0; e < 4; e++) { const float lo = bf_lo(u[e]), hi = bf_hi(u[e]); s0 += lo; s1 += hi; q0 += lo * lo; q1 += hi * hi; }
          }
          s0 += s1; q0 += q1;
#pragma unroll
          for (int o = 16; o > 0; o >>= 1) { s0 += __shfl_xor_sync(0xffffffffu, s0, o); q0 += __shfl_xor_sync(0xffffffffu, q0, o); }
          const float mean = s0 * (1.f / DM);
          float mb, sd;
          ln_scalars(mean, fmaxf(q0 * (1.f / DM) - mean * mean, 0.f), mb, sd);
          uint32_t ih, il;
          split_inv(sd, ih, il);
          if (lane == 0) st_b128(pln + part * 16, pack_bf(mb, mb), ih, il, tag);
          PROF(1, tid == 0 && part == 2, 4);
        } else if (late == (part == 3)) {
          const uint32_t fr = (lane & 7) + (lane >> 4) * 8, tq = lane & 3;
          const uint32_t wa = stage + warp * 4096 + fr * 64 + ((((lane >> 3) & 1) ^ ((fr >> 1) & 3)) << 4);
          float d0[4] = {0.f, 0.f, 0.f, 0.f}, d1[4] = {0.f, 0.f, 0.f, 0.f};
          mbar_wait(bar_hw, 0);
#pragma unroll
          for (int ks = 0; ks < 4; ks++) {
            uint32_t w[8];
            ldmatrix4t(wa + ks * 1024, w[0], w[1], w[2], w[3]);
            ldmatrix4t((wa ^ 32) + ks * 1024, w[4], w[5], w[6], w[7]);
            mma16816(d0, w[0], w[1], w[2], w[3], sc[2 * ks], sc[2 * ks + 1]);
            mma16816(d1, w[4], w[5], w[6], w[7], sc[2 * ks], sc[2 * ks + 1]);
          }
          sts1(base + 2 * GST_BYTES + warp * 2048 + (tq * 8 + (lane >> 2)) * 4, __float_as_uint((tq & 2) ? ((tq & 1) ? d1[2] : d1[0]) : ((tq & 1) ? d0[2] : d0[0])));
          bar_sync(1, 256);
          if (warp == 0) {
            float s = 0.f;
#pragma unroll
            for (int w8 = 0; w8 < 8; w8++) s += __uint_as_float(lds1(base + 2 * GST_BYTES + w8 * 2048 + lane * 4));
            st_relaxed(pmod, (__float_as_uint(s) & ~3u) | tag);
          }
          PROF(1, tid == 0, 3);
        }
      }
      cluster_wait();
      if (wg == 1) bar_arrive(2, 256);
    }

    float f0 = 0.f, f1 = 0.f;
    const uint32_t rempty = lane < 2 ? mapa(bempty, lane & 1) : 0;
    constexpr uint32_t GE = NSLOT * 8 + 32;
    float o[64], s[64];
#pragma unroll 1
    for (int ps = 0; ps < 3; ps++) {
      {
        const uint32_t xt = ps == 1 ? XT1 : XT2, wt = ps == 1 ? WT1 : WT2;
        const int nst = ps == 2 ? 28 : 14;
        if (ps == 0) {
          float ga[64], gb[64];
#pragma unroll
          for (int i = 0; i < 64; i++) { ga[i] = 0.f; gb[i] = 0.f; }
          uint32_t a[2][16];
          const uint32_t l = fresh_lane();
          uint32_t fa[4];
#pragma unroll
          for (int kk = 0; kk < 4; kk++) fa[kk] = (base + wg * 8192 + frag_offset(warp)) ^ (kk * 32);
          const uint32_t mt = par + (l & 3) * 16;
          auto fetch = [&](int i, uint32_t (&f)[16], uint32_t z) {
            mbar_wait(xfull + (i & 3) * 8, i >> 2);
#pragma unroll
            for (int kk = 0; kk < 4; kk++) ldmatrix4(fa[kk] + (i & 3) * GST_BYTES + z, f[4 * kk], f[4 * kk + 1], f[4 * kk + 2], f[4 * kk + 3]);
          };
          const bool oddw = warp & 2;
          uint4 r0, r1;
          {
            const uint32_t t7 = (warp & 1) * 64 + (l >> 4) * 32 + (l & 15);
            const uint32_t* pm = g_modp + wg * DM + ((cj * 128 + t7 * 4) & (DM - 1));
            const uint32_t* pr = g_ln1 + (rb * 128 + warp * 16 + (l >> 2)) * 4;
            uint4 m0 = make_uint4(tag, tag, tag, tag), m1 = m0;
            if (!oddw) { m0 = ld_relaxed4(pm); m1 = ld_relaxed4(pm + 2 * DM); }
            r0 = ld_b128(pr); r1 = ld_b128(pr + 32);
            fetch(0, a[0], 0); fetch(1, a[1], 0);
            uint32_t n = 0;
            bool written = false;
#pragma unroll 1
            while (true) {
              uint32_t miss;
              asm volatile("{ .reg .pred p0, p1, p2, p3; .reg .b32 t, u;\n"
                           "lop3.b32 t, %1, %2, %19, 0x7e; lop3.b32 u, %3, %4, %19, 0x7e; or.b32 t, t, u; and.b32 t, t, 3; setp.ne.u32 p0, t, 0;\n"
                           "lop3.b32 t, %5, %6, %19, 0x7e; lop3.b32 u, %7, %8, %19, 0x7e; or.b32 t, t, u; and.b32 t, t, 3; setp.ne.u32 p1, t, 0;\n"
                           "setp.ne.u32 p2, %12, %19; setp.ne.u32 p3, %16, %19;\n"
                           "@p0 ld.relaxed.gpu.global.v4.u32 {%1, %2, %3, %4}, [%17];\n"
                           "@p1 ld.relaxed.gpu.global.v4.u32 {%5, %6, %7, %8}, [%17 + 8192];\n"
                           "@p2 ld.relaxed.gpu.global.v4.u32 {%9, %10, %11, %12}, [%18];\n"
                           "@p3 ld.relaxed.gpu.global.v4.u32 {%13, %14, %15, %16}, [%18 + 128];\n"
                           "or.pred p0, p0, p1; or.pred p2, p2, p3; vote.sync.any.pred p0, p0, 0xffffffff; vote.sync.any.pred p2, p2, 0xffffffff;\n"
                           "selp.u32 t, 1, 0, p0; selp.u32 u, 2, 0, p2; or.b32 %0, t, u; }"
                           : "=r"(miss), "+r"(m0.x), "+r"(m0.y), "+r"(m0.z), "+r"(m0.w), "+r"(m1.x), "+r"(m1.y), "+r"(m1.z), "+r"(m1.w),
                             "+r"(r0.x), "+r"(r0.y), "+r"(r0.z), "+r"(r0.w), "+r"(r1.x), "+r"(r1.y), "+r"(r1.z), "+r"(r1.w)
                           : "l"(pm), "l"(pr), "r"(tag) : "memory");
              if (!(miss & 1) && !written) {
                written = true;
                if (!oddw) write_table(par, wg, t7, m0, m1);
                mbar_arrive(bar_mod);
              }
              if (!miss) break;
              watchdog(n);
            }
          }
          const uint32_t zero = r0.w ^ tag;
          auto normalize = [&](uint32_t (&f)[16]) {
#pragma unroll
            for (int k = 0; k < 16; k += 2) { f[k] = ln_norm(f[k], r0.x, r0.y, r0.z); f[k + 1] = ln_norm(f[k + 1], r1.x, r1.y, r1.z); }
          };
          auto modulate = [&](int i, uint32_t (&f)[16]) {
#pragma unroll
            for (int kk = 0; kk < 4; kk++) {
              const uint4 m = lds4(mt + slice_of(i) * 256 + kk * 64);
              f[4 * kk] = MODUL(f[4 * kk], m.x, m.z); f[4 * kk + 1] = MODUL(f[4 * kk + 1], m.x, m.z);
              f[4 * kk + 2] = MODUL(f[4 * kk + 2], m.y, m.w); f[4 * kk + 3] = MODUL(f[4 * kk + 3], m.y, m.w);
            }
            keep(f);
            mbar_arrive_pred(xempty + (i & 3) * 8, l == 0);
          };
          auto publish = [&](int u, uint32_t (&f)[16]) {
#pragma unroll
            for (int kk = 0; kk < 4; kk++) stmatrix4(fa[kk] + OFF_STAGE + u * UNIT, f[4 * kk], f[4 * kk + 1], f[4 * kk + 2], f[4 * kk + 3]);
            __syncwarp();
            mbar_arrive_pred(bar_hpub + u * 8, l == 0);
          };
          auto multiply = [&](int i, uint32_t (&f)[16]) {
            mbar_wait(gfull + (i & 3) * 8, i >> 2);
            const uint64_t db = make_desc(base + (i & 3) * GST_BYTES + UNIT, 8192, 1024);
            wg_fence();
#pragma unroll
            for (int kk = 0; kk < 4; kk++) mma256_rs(ga, gb, f[4 * kk], f[4 * kk + 1], f[4 * kk + 2], f[4 * kk + 3], db + kk * 128);
            wg_commit();
          };
          auto next = [&](int i, uint32_t (&f)[16]) {
            wg_wait<1>();
            mbar_arrive_cl(rempty, GE + ((i + 2) & 3) * 8);
            uint32_t z = zero;
#pragma unroll
            for (int k = 0; k < 16; k += 2) asm volatile("lop3.b32 %0, %1, %2, %0, 0xA8;" : "+r"(z) : "r"(f[k]), "r"(f[k + 1]));
            fetch(i, f, z);
            normalize(f);
            if (i == 2) { keep(f); mbar_wait(bar_mod2, 0); }
            modulate(i, f); multiply(i, f);
          };
          normalize(a[0]); normalize(a[1]);
          keep(a[0]); keep(a[1]);
          mbar_wait(bar_mod, 0);
          PROF(1, tid == 0, 2);
          modulate(0, a[0]); multiply(0, a[0]); publish(0, a[0]);
          modulate(1, a[1]); multiply(1, a[1]);
#pragma unroll 1
          for (int i = 2; i < NRS; i += 2) {
            next(i, a[0]);
            if (i == 2) publish(1, a[0]);
            next(i + 1, a[1]);
          }
          wg_wait<1>();
          mbar_arrive_cl(rempty, GE + ((NRS + 2) & 3) * 8);
#pragma unroll 1
          for (int i = NRS; i < 14; i++) {
            mbar_wait(xfull + (i & 3) * 8, (i >> 2) & 1);
            mbar_wait(gfull + (i & 3) * 8, (i >> 2) & 1);
            const uint32_t xa = base + (i & 3) * GST_BYTES;
            const uint64_t da = make_desc(xa + wg * 8192, 16, 1024), db = make_desc(xa + UNIT, 8192, 1024);
            if (i == 13) bar_sync(2 + wg, 256);
            wg_fence();
#pragma unroll
            for (int kk = 0; kk < 4; kk++) mma256_ss(ga, gb, da + kk * 2, db + kk * 128, 1);
            wg_commit();
            if (i == 13) bar_arrive(3 - wg, 256);
            wg_wait<1>();
            uint32_t z = zero;
#pragma unroll
            for (int k = 0; k < 16; k += 2) asm volatile("lop3.b32 %0, %1, %2, %0, 0xA8;" : "+r"(z) : "r"(a[1][k]), "r"(a[1][k + 1]));
            mbar_arrive_cl(rempty, GE + ((i + 3) & 3) * 8 + z);
            mbar_arrive_pred(xempty + ((i + 3) & 3) * 8, l == 0 && i != NRS);
          }
          mbar_wait(xfull + 16, 1);
          wg_wait<0>();
          keep(ga); keep(gb);
#pragma unroll
          for (int i = 0; i < 64; i++) {
            asm volatile("mov.b32 %0, %1;" : "=f"(s[i]) : "f"(ga[i]));
            asm volatile("mov.b32 %0, %1;" : "=f"(o[i]) : "f"(gb[i]));
          }
        } else {
          float ga[64], gb[64];
#pragma unroll
          for (int i = 0; i < 64; i++) {
            asm volatile("mov.b32 %0, %1;" : "=f"(ga[i]) : "f"(s[i]));
            asm volatile("mov.b32 %0, %1;" : "=f"(gb[i]) : "f"(o[i]));
          }
#pragma unroll 1
          for (int i = 2; i < nst; i++) {
            mbar_wait(gfull + (i & 3) * 8, (i >> 2) & 1);
            const uint64_t da = make_desc(base + unit_of(xt, i & 3) + wg * 8192, 16, 1024), db = make_desc(base + unit_of(wt, i & 3), 8192, 1024);
            if (i == nst - 1) bar_sync(2 + wg, 256);
            wg_fence();
#pragma unroll
            for (int kk = 0; kk < 4; kk++) mma256_ss(ga, gb, da + kk * 2, db + kk * 128, 1);
            wg_commit();
            if (i == nst - 1) bar_arrive(3 - wg, 256);
            wg_wait<1>();
            mbar_arrive_cl(rempty, GE + ((i + 3) & 3) * 8, i != 2);
            PROF(4, tid == 0 && (i & 3) == 0, 40 + (ps - 1) * 4 + i / 4);
          }
          wg_wait<0>();
          keep(ga); keep(gb);
#pragma unroll
          for (int i = 0; i < 64; i++) {
            asm volatile("mov.b32 %0, %1;" : "=f"(s[i]) : "f"(ga[i]));
            asm volatile("mov.b32 %0, %1;" : "=f"(o[i]) : "f"(gb[i]));
          }
        }
        mbar_arrive_cl(rempty, GE + (ps == 2 ? 24 : 8));
        if (ps == 2) break;
      }
      const uint32_t qw = base + wg * 8192, qt = QT >> (16 * ps), at = ps ? AT1 : AT0;
      {
        const uint32_t wt = ps ? WT1 : WT0;
        const uint64_t da0 = make_desc(qw + unit_of(qt, 2), 16, 1024), da1 = make_desc(qw + unit_of(qt, 3), 16, 1024);
        const uint64_t db0 = make_desc(base + unit_of(wt, 2), 8192, 1024), db1 = make_desc(base + unit_of(wt, 3), 8192, 1024);
        mbar_wait(gfull + 16, 1);
        bar_sync(2 + wg, 256);
        wg_fence();
#pragma unroll
        for (int kk = 0; kk < 4; kk++) mma_ss<1>(s, da0 + kk * 2, db0 + kk * 128, 1);
        wg_commit();
        mbar_wait(xfull + 24, 1);
        mbar_wait(gfull + 24, 1);
        wg_fence();
#pragma unroll
        for (int kk = 0; kk < 4; kk++) mma_ss<1>(s, da1 + kk * 2, db1 + kk * 128, 1);
        wg_commit();
        bar_arrive(3 - wg, 256);
        mbar_wait(ps == 0 ? bar_pread : bar_ofree + 8, 0);
        wg_wait<0>();
        keep(s);
        PROF(2, tid == 0, 8 + ps * 8);
        uint32_t q[32];
        pack_p(s, q);
#pragma unroll
        for (int i = 0; i < 4; i++) stmatrix4((qw + unit_of(qt, 0) + frag_offset(warp)) ^ (i << 5), q[4 * i], q[4 * i + 1], q[4 * i + 2], q[4 * i + 3]);
        keep(q);
        bar_sync(2 + wg, 256);
        wg_fence();
#pragma unroll
        for (int kk = 0; kk < 8; kk++) mma_ss<1>(o, (kk < 4 ? da0 : da1) + (kk & 3) * 2, (kk < 4 ? db0 : db1) + UNIT / 16 + (kk & 3) * 128, 1);
        wg_commit();
        mbar_wait(bfull, 0);
        wg_fence();
        const uint64_t dk = make_desc(base + unit_of(at, 0), 16, 1024);
#pragma unroll
        for (int kk = 0; kk < 8; kk++) mma_rs<0>(s, q[4 * kk], q[4 * kk + 1], q[4 * kk + 2], q[4 * kk + 3], dk + (kk >> 2) * 1024 + (kk & 3) * 2, kk != 0);
        wg_commit();
        bar_arrive(3 - wg, 256);
#pragma unroll
        for (int i = 4; i < 8; i++) stmatrix4((qw + unit_of(qt, 1) + frag_offset(warp)) ^ ((i & 3) << 5), q[4 * i], q[4 * i + 1], q[4 * i + 2], q[4 * i + 3]);
        wg_wait<1>();
        keep(o);
        mbar_arrive_cl(rempty, GE + 16);
        mbar_arrive_cl(rempty, GE + 24);
        store_chunk<0>(o, qw + unit_of(qt, 2) + frag_offset(warp));
        store_chunk<1>(o, qw + unit_of(qt, 3) + frag_offset(warp));
        wg_wait<0>();
        keep(s);
        mbar_arrive_cl(rempty, 0);
      }
      PROF(4, tid == 0 && ps == 1, 61);
      float l0 = 0.f, l1 = 0.f;
      auto step = [&](auto odd_c, const int j, uint32_t (&pw)[32], uint32_t (&pr)[32]) {
        constexpr bool ODD = decltype(odd_c)::value;
        const bool first = !ODD && (j & 2) == 0, last = ODD && j == 7;
        const uint32_t ph = (j >> 1) & 1;
        float i0, i1, a0, a1;
        const bool so = !ODD && j == 4;
        if (so) { i0 = inv_quad_sum(l0); i1 = inv_quad_sum(l1); l0 = 0.f; l1 = 0.f; }
        bool redo = !ODD && (j | ps) == 0;
        while (true) {
          if (redo) {
            float m0 = fmaxf(s[0], s[1]), m1 = fmaxf(s[2], s[3]);
#pragma unroll
            for (int i = 1; i < 16; i++) { m0 = fmaxf(m0, fmaxf(s[4 * i], s[4 * i + 1])); m1 = fmaxf(m1, fmaxf(s[4 * i + 2], s[4 * i + 3])); }
            m0 = fmaxf(m0, __shfl_xor_sync(0xffffffffu, m0, 1)); m1 = fmaxf(m1, __shfl_xor_sync(0xffffffffu, m1, 1));
            m0 = fmaxf(m0, __shfl_xor_sync(0xffffffffu, m0, 2)); m1 = fmaxf(m1, __shfl_xor_sync(0xffffffffu, m1, 2));
            m0 *= SCL2; m1 *= SCL2;
            if (!first) {
              m0 = fmaxf(m0, f0); m1 = fmaxf(m1, f1);
              const float c0 = ex2(f0 - m0), c1 = ex2(f1 - m1);
              l0 *= c0; l1 *= c1;
              wg_wait<0>();
              keep(o);
#pragma unroll
              for (int i = 0; i < 16; i++) { o[4 * i] *= c0; o[4 * i + 1] *= c0; o[4 * i + 2] *= c1; o[4 * i + 3] *= c1; }
            }
            f0 = m0; f1 = m1;
          }
          float b0 = 0.f, b1 = 0.f;
          a0 = 0.f; a1 = 0.f;
#pragma unroll
          for (int i = 0; i < 16; i++) {
            const float e0 = ex2(fmaf(s[4 * i], SCL2, -f0)), e1 = ex2(fmaf(s[4 * i + 1], SCL2, -f0));
            const float e2 = ex2(fmaf(s[4 * i + 2], SCL2, -f1)), e3 = ex2(fmaf(s[4 * i + 3], SCL2, -f1));
            a0 += e0; b0 += e1; a1 += e2; b1 += e3;
            pw[2 * i] = pack_bf(e0, e1); pw[2 * i + 1] = pack_bf(e2, e3);
            if (i == VREL) {
#pragma unroll
              for (int k = 0; k < 2 * VREL + 2; k++) asm volatile("" : "+r"(pw[k])::"memory");
              mbar_wait(bar_mod, 0);
              wg_wait<0>();
              mbar_arrive_cl(rempty, ODD ? 16 : 0, !redo && (ODD || j));
#pragma unroll
              for (int k = 4 * VREL + 4; k < 64; k++) asm volatile("" : "+f"(s[k])::"memory");
            }
          }
          a0 += b0; a1 += b1;
          if (redo) break;
          redo = __any_sync(0xffffffffu, !(a0 + a1 < 0x1p90f));
          if (first) {
            uint32_t m0 = __ballot_sync(0xffffffffu, a0 > 0x1p-80f), m1 = __ballot_sync(0xffffffffu, a1 > 0x1p-80f);
            m0 |= m0 >> 1; m1 |= m1 >> 1; m0 |= m0 >> 2; m1 |= m1 >> 2;
            redo = redo || (m0 & m1 & 0x11111111u) != 0x11111111u;
          }
          if (!redo) break;
        }
        l0 += a0; l1 += a1;
        keep(pw);
        keep(o);
        if (so) store_chunk<0>(o, i0, i1, qw + unit_of(qt, 0) + frag_offset(warp));
        keep(o);
        if (j == (ODD ? 5 : 0)) { fence_async_smem(); if (ODD) mbar_arrive(bar_ofull + wg * 8); }
        mbar_wait(bfull + (ODD ? 24 : 8), ph);
        bar_sync(2 + wg, 256);
        if (!last) {
          const uint32_t qn = qt >> (j >= 3 ? 8 : 0);
          wg_fence();
          issue_qk(s, qw + unit_of(qn, 0), qw + unit_of(qn, 1), base + unit_of(at, ODD ? 3 : 1));
          wg_commit();
          mbar_wait(bfull + (ODD ? 0 : 16), ODD ? ph ^ 1 : ph);
        }
        if (so) { store_chunk<1>(o, i0, i1, qw + unit_of(qt, 1) + frag_offset(warp)); keep(o); }
        wg_fence();
        issue_pv(o, pw, base + unit_of(at, ODD ? (last ? 3 : 0) : 2), !first);
        wg_commit();
        bar_arrive(3 - wg, 256);
        wg_wait<1>();
        keep(s);
        mbar_arrive_cl(rempty, ODD ? 24 : 8, !last);
        PROF(4, tid == 0 && ps == 1, 51 + j);
      };
      uint32_t pa[32], pb[32];
#pragma unroll 1
      for (int j = 0; j < 8; j += 2) {
        step(std::false_type{}, j, pa, pb);
        step(std::true_type{}, j + 1, pb, pa);
      }
      {
        const uint64_t dx = make_desc(qw + unit_of(ps ? XT2 : XT1, 0), 16, 1024), dw = make_desc(base, 8192, 1024);
        mbar_wait(gfull, 0);
        wg_fence();
#pragma unroll
        for (int kk = 0; kk < 8; kk++) mma_ss<1>(s, dx + (kk >> 2) * (UNIT / 16) + (kk & 3) * 2, dw + (kk >> 2) * (UNIT / 16) + (kk & 3) * 128, kk != 0);
        wg_commit();
        const float i0 = inv_quad_sum(l0), i1 = inv_quad_sum(l1);
        wg_wait<1>();
        keep(o);
        mbar_arrive_cl(rempty, 24);
        store_chunk<0>(o, i0, i1, qw + unit_of(qt, 2) + frag_offset(warp));
        store_chunk<1>(o, i0, i1, qw + unit_of(qt, 3) + frag_offset(warp));
        keep(o);
        mbar_wait(gfull + 8, 0);
        bar_sync(2 + wg, 256);
        wg_fence();
#pragma unroll
        for (int kk = 0; kk < 8; kk++) mma_ss<1>(o, dx + (kk >> 2) * (UNIT / 16) + (kk & 3) * 2, dw + (2 + (kk >> 2)) * (UNIT / 16) + (kk & 3) * 128, kk != 0);
        wg_commit();
        bar_arrive(3 - wg, 256);
        wg_wait<0>();
        keep(s); keep(o);
        mbar_arrive_cl(rempty, GE);
        mbar_arrive_cl(rempty, GE + 8);
        fence_async_smem();
        mbar_arrive(bar_ofull + 16 + wg * 8);
      }
      PROF(2, tid == 0, 10 + ps * 8);
    }

    const int ln = fresh_lane(), g = ln >> 2, tq = ln & 3, ct = warp * 32 + ln;
    const bool lane0 = ln == 0;
    const int lrow0 = warp * 16 + g;
    const int grow0 = rb * 128 + lrow0;
    const uint32_t res = base + OFF_RES, trow = res + wg * 8192 + frag_offset(warp);
    uint32_t xr[32];
    uint4 sv[4], own;
    uint32_t* sp[4];
#pragma unroll
    for (int k = 0; k < 4; k++) sp[k] = g_stats + ((((tq >> 1) * 4 + k) ^ cj) * SEQ + grow0 + (tq & 1) * 8) * 4;
    {
      const uint64_t da = make_desc(base + wg * 8192, 16, 1024), db = make_desc(base, 8192, 1024);
      constexpr int U = UNIT / 16;
#define HALF_STAGE(acc, xu, wu) _Pragma("unroll") for (int kk = 0; kk < 4; kk++) mma_ss<1>(acc, da + (xu) * U + kk * 2, db + (wu) * U + kk * 128, 1)
      PROF(10, ct == PT, 19); STAMP(0);
      cluster_arrive();
      mbar_wait(gfull, 1);
      mbar_wait(gfull + 8, 1);
      bar_sync(2 + wg, 256);
      wg_fence();
      HALF_STAGE(o, 7, 1);
      HALF_STAGE(o, 8, 3);
      wg_commit();
      STAMP(16);
      mbar_wait(gfull + 16, 1);
      STAMP(17);
      wg_fence();
      HALF_STAGE(o, 6, 11);
      wg_commit();
      bar_arrive(3 - wg, 256);
      mbar_wait(bar_par, 0);
      uint32_t* xo = g_xch + ((size_t)b * 8 * 256 + ct) * 4;
      const uint32_t* xi = g_xch + ((size_t)(b ^ 2) * 8 * 256 + ct) * 4;
      const uint32_t par1 = (~lds1(par + PAR_CONST + 4) & 1) << 16;
      wg_wait<1>();
      mbar_arrive_pred(bar_rel, lane0);
      wg_wait<0>();
      keep(o);
      mbar_arrive_pred(bar_ring, lane0);
      PROF(8, ct == PT, 20); STAMP(1);
#define SEND(i) st_b128(xo + (i) * 1024, (pack_bf(o[8 * (i)], o[8 * (i) + 1]) & ~0x10000u) | par1, pack_bf(o[8 * (i) + 2], o[8 * (i) + 3]), \
                        pack_bf(o[8 * (i) + 4], o[8 * (i) + 5]), pack_bf(o[8 * (i) + 6], o[8 * (i) + 7]))
#pragma unroll
      for (int i = 0; i < NS1; i++) SEND(i);
      PROF(8, ct == PT, 21); STAMP(2);
      bar_sync(2 + wg, 256);
      wg_fence();
      HALF_STAGE(s, 7, 0);
      HALF_STAGE(s, 8, 2);
      HALF_STAGE(s, 6, 10);
      wg_commit();
      bar_arrive(3 - wg, 256);
      STAMP(18);
      mbar_wait(gfull + 24, 1);
#pragma unroll
      for (int i = NS1; i < 8; i++) SEND(i);
      uint4 v[8];
#pragma unroll
      for (int i = 0; i < LD1; i++) v[i] = ld_b128(xi + i * 1024);
      STAMP(19);
      mbar_wait(bar_xres, 0);
      wg_wait<0>();
      mbar_arrive_pred(bar_ring + 8, lane0);
      bar_sync(2 + wg, 256);
      STAMP(20);
#pragma unroll
      for (int i = LD1; i < LD2; i++) v[i] = ld_b128(xi + i * 1024);
      mbar_wait(bar_xres, 0);
      wg_fence();
      HALF_STAGE(s, 9, 4);
      wg_commit();
      mbar_wait(bar_rx, 0);
      wg_fence();
      HALF_STAGE(s, 1, 5);
      wg_commit();
      bar_arrive(3 - wg, 256);
      STAMP(21);
#pragma unroll
      for (int i = LD2; i < 8; i++) v[i] = ld_b128(xi + i * 1024);
      if (LD2 < 8) mbar_wait(bar_xres, 0);
      wg_wait<0>();
      keep(s);
      mbar_arrive_pred(bar_ring + 16, lane0);
      PROF(10, ct == PT, 23); STAMP(4);
#pragma unroll
      for (int i = 0; i < 16; i += 2) ldmatrix4((trow ^ ((i & 7) << 4)) + (i >> 3) * 16384, xr[2 * i], xr[2 * i + 1], xr[2 * i + 2], xr[2 * i + 3]);
      uint32_t ga[16];
      uint4 bw[8];
#pragma unroll
      for (int i = 0; i < 8; i++) {
        if (!(i & 1)) {
          const uint4 t = lds4(par + PAR_SINK + i * 32 + tq * 16);
          ga[2 * i] = t.x; ga[2 * i + 1] = t.y; ga[2 * i + 2] = t.z; ga[2 * i + 3] = t.w;
        }
        bw[i] = lds4(par + PAR_T1 + i * 64 + tq * 16);
        if (!(g & 1)) { bw[i].x = 0x3f803f80u; bw[i].y = 0x3f803f80u; }
      }
      uint32_t pk[32];
      pack_p(s, pk);
      keep(pk);
      {
        uint32_t n = 0, miss;
        do {
          miss = 0;
#pragma unroll
          for (int i = 0; i < 8; i++) miss |= v[i].x ^ par1;
          miss = __any_sync(0xffffffffu, miss & 0x10000u);
          if (miss) {
#pragma unroll
            for (int i = 0; i < 8; i++)
              asm volatile("{ .reg .pred p; .reg .b32 t; xor.b32 t, %0, %5; and.b32 t, t, 0x10000; setp.ne.u32 p, t, 0;\n"
                           "@p ld.relaxed.gpu.global.v4.u32 {%0, %1, %2, %3}, [%4]; }"
                           : "+r"(v[i].x), "+r"(v[i].y), "+r"(v[i].z), "+r"(v[i].w) : "l"(xi + i * 1024), "r"(par1) : "memory");
          }
          watchdog(n);
        } while (miss);
      }
      PROF(8, ct == PT, 22); STAMP(3);
      float ds[4] = {0.f, 0.f, 0.f, 0.f}, dl[4] = {0.f, 0.f, 0.f, 0.f}, q0[4] = {0.f, 0.f, 0.f, 0.f}, q1[4] = {0.f, 0.f, 0.f, 0.f};
#pragma unroll
      for (int i = 0; i < 8; i++) {
        const uint32_t u0 = hfma2(ga[2 * i], hadd2(pk[4 * i], v[i].x & ~0x10000u), xr[4 * i]);
        const uint32_t u1 = hfma2(ga[2 * i], hadd2(pk[4 * i + 1], v[i].y), xr[4 * i + 1]);
        const uint32_t u2 = hfma2(ga[2 * i + 1], hadd2(pk[4 * i + 2], v[i].z), xr[4 * i + 2]);
        const uint32_t u3 = hfma2(ga[2 * i + 1], hadd2(pk[4 * i + 3], v[i].w), xr[4 * i + 3]);
        xr[4 * i] = u0; xr[4 * i + 1] = u1; xr[4 * i + 2] = u2; xr[4 * i + 3] = u3;
        mma16816(ds, u0, u1, u2, u3, bw[i].x, bw[i].y);
        mma16816(dl, u0, u1, u2, u3, bw[i].z, bw[i].w);
        mma16816(q0, u0, u1, u2, u3, u0, u2);
        mma16816(q1, u0, u1, u2, u3, u1, u3);
      }
      const float sqa = __shfl_sync(0xffffffffu, (g & 1) ? q0[1] : q0[0], g * 4 + (g >> 1));
      const float sqb = __shfl_sync(0xffffffffu, (g & 1) ? q1[3] : q1[2], g * 4 + (g >> 1));
      own = (tq & 1) ? make_uint4(__float_as_uint(ds[2]), __float_as_uint(sqb), __float_as_uint(ds[3] + dl[3]), tag)
                                 : make_uint4(__float_as_uint(ds[0]), __float_as_uint(sqa), __float_as_uint(ds[1] + dl[1]), tag);
      if (tq < 2) st_b128(sp[0], own.x, own.y, own.z, own.w);
#pragma unroll
      for (int k = 0; k < 4; k++) sv[k] = make_uint4(0, 0, 0, 0);
    }
    PROF(8, ct == PT, 29); STAMP(5);
    uint32_t mm, ih, il;
    float rbest;
    uint32_t wf[128];
    const uint32_t frow = (ln & 7) + (ln >> 4) * 8;
    const uint32_t wfo = base + (warp & 1) * 8192 + frow * 64 + ((((ln >> 3) & 1) ^ ((frow >> 1) & 3)) << 4);
#define LOAD_WF(m) _Pragma("unroll") for (int f = 0; f < 16; f++) {                                                   \
      const int r = ((f >> 1) * 4 + (m) * 2 + (f & 1)) * 4;                                                           \
      ldmatrix4t(((wfo + unit_of((m) ? FT_U : FT_G, warp >> 1)) ^ ((f & 1) * 32)) + (f >> 1) * 1024, wf[r], wf[r + 1], wf[r + 2], wf[r + 3]); \
    }
    bool early;
    {
#pragma unroll
      for (int i = 0; i < 16; i += 2) stmatrix4((trow ^ ((i & 7) << 4)) + (i >> 3) * 16384, xr[2 * i], xr[2 * i + 1], xr[2 * i + 2], xr[2 * i + 3]);
      const uint4 cst = lds4(par + PAR_CONST);
      const float A1 = __uint_as_float(cst.x), A2 = __uint_as_float(cst.z);
      uint32_t n = 0;
      early = false;
#pragma unroll 1
      while (true) {
        uint32_t miss;
        asm volatile("{ .reg .pred p0, p1, p2, p3; .reg .b64 u, v; .reg .b128 w;\n"
                     "setp.ge.u32 p0, %22, 2; setp.ne.and.u32 p0, %4, %21, p0; setp.ne.u32 p1, %8, %21; setp.ne.u32 p2, %12, %21; setp.ne.u32 p3, %16, %21;\n"
                     "@p0 ld.relaxed.gpu.global.v4.u32 {%1, %2, %3, %4}, [%17];\n"
                     "@p1 ld.relaxed.gpu.global.v4.u32 {%5, %6, %7, %8}, [%18];\n"
                     "@p2 ld.relaxed.gpu.global.v4.u32 {%9, %10, %11, %12}, [%19];\n"
                     "@p3 ld.relaxed.gpu.global.v4.u32 {%13, %14, %15, %16}, [%20];\n"
                     "or.pred p0, p0, p1; or.pred p2, p2, p3; or.pred p0, p0, p2; vote.sync.any.pred p0, p0, 0xffffffff; selp.u32 %0, 1, 0, p0; }"
                     : "=r"(miss), "+r"(sv[0].x), "+r"(sv[0].y), "+r"(sv[0].z), "+r"(sv[0].w), "+r"(sv[1].x), "+r"(sv[1].y), "+r"(sv[1].z), "+r"(sv[1].w),
                       "+r"(sv[2].x), "+r"(sv[2].y), "+r"(sv[2].z), "+r"(sv[2].w), "+r"(sv[3].x), "+r"(sv[3].y), "+r"(sv[3].z), "+r"(sv[3].w)
                     : "l"(sp[0]), "l"(sp[1]), "l"(sp[2]), "l"(sp[3]), "r"(tag), "r"(tq) : "memory");
        if (!miss) break;
        if (!early && (b >= NFFN || __all_sync(0xffffffffu, mbar_test(bar_box + (warp >> 1) * 8, 0)))) {
          early = true;
          LOAD_WF(0);
          __syncwarp();
          mbar_arrive_pred(bar_gate, lane0);
        }
        watchdog(n);
      }
      const uint4 v0 = tq < 2 ? own : sv[0], v1 = sv[1], v2 = sv[2], v3 = sv[3];
      PROF(8, ct == PT, 30); STAMP(6);
      float su = (__uint_as_float(v0.x) + __uint_as_float(v1.x)) + (__uint_as_float(v2.x) + __uint_as_float(v3.x));
      float sq = (__uint_as_float(v0.y) + __uint_as_float(v1.y)) + (__uint_as_float(v2.y) + __uint_as_float(v3.y));
      float dt = (__uint_as_float(v0.z) + __uint_as_float(v1.z)) + (__uint_as_float(v2.z) + __uint_as_float(v3.z));
      su += __shfl_xor_sync(0xffffffffu, su, 2); sq += __shfl_xor_sync(0xffffffffu, sq, 2); dt += __shfl_xor_sync(0xffffffffu, dt, 2);
      const float m = su * (1.f / DM);
      float mb, sd;
      ln_scalars(m, fmaxf(sq * (1.f / DM) - m * m, 0.f), mb, sd);
      const float inv = rcp(sd);
      rbest = (dt - mb * A1) * inv + A2;
      mm = pack_bf(mb, mb);
      ih = pack_bf(inv, inv);
      const float lo = inv - bf_lo(ih);
      il = pack_bf(lo, lo);
    }
    int ibest;
    {
      const uint32_t bits = __float_as_uint(rbest);
      const uint32_t key = (((int)bits < 0 ? ~bits : bits | 0x80000000u) & ~0x1ffu) | ((127 - lrow0 - (tq & 1) * 8) << 2) | tag;
      sts1(par + PAR_RED + warp * 4, __reduce_max_sync(0xffffffffu, key));
      PROF(8, ct == PT, 38); STAMP(7);
      bar_sync(1, 256);
      const uint4 ka = lds4(par + PAR_RED), kb = lds4(par + PAR_RED + 16);
      const uint32_t k2 = max(max(max(ka.x, ka.y), max(ka.z, ka.w)), max(max(kb.x, kb.y), max(kb.z, kb.w)));
      if (ct < CR && cj == 0) st_relaxed(g_cand + ct * 512 + rb * CS, k2);
      ibest = 127 - ((k2 >> 2) & 127);
    }
    PROF(8, ct == PT, 39); STAMP(8);
    if ((ibest >> 4) == warp) {
      const int src = (ibest & 7) * 4 + ((ibest >> 3) & 1), ch = g * 2;
      const uint32_t cm = __shfl_sync(0xffffffffu, mm, src), ch_ = __shfl_sync(0xffffffffu, ih, src), cl = __shfl_sync(0xffffffffu, il, src);
      const uint32_t xa = res + (ch >> 3) * 16384 + ibest * 128 + (((ch & 7) ^ (ibest & 7)) << 4) + tq * 4;
      const uint32_t x0 = lds1(xa), x1 = lds1(xa ^ 16);
      const uint2 p0 = lds2(par + PAR_T2 + ch * 64 + tq * 16), p1 = lds2(par + PAR_T2 + ch * 64 + 64 + tq * 16);
      uint32_t* dst = g_row + rb * 2 * DM + cj * 128 + ln * 4;
      st_pairs(dst, ln_mod(x0, cm, ch_, cl, p0.x, p0.y), ln_mod(x1, cm, ch_, cl, p1.x, p1.y), tag);
      st_pairs(dst + DM, x0, x1, tag);
      __syncwarp();
    }
    PROF(8, ct == PT, 37); STAMP(9);
    uint32_t wd[64];
    const uint32_t wda = base + unit_of(FT_D, warp >> 1) + (warp & 1) * 8192 + frow * 128 + ((((ln >> 3) & 1) ^ (ln & 7)) << 4);
#define LOAD_WD(f) ldmatrix4t((wda ^ ((((f) >> 1) & 3) * 32)) + ((f) >> 3) * 4096 + ((f) & 1) * 2048, wd[4 * (f)], wd[4 * (f) + 1], wd[4 * (f) + 2], wd[4 * (f) + 3])
    if (!early) {
      if (b < NFFN) mbar_wait(bar_box + (warp >> 1) * 8, 0);
      LOAD_WF(0);
      __syncwarp();
      mbar_arrive_pred(bar_gate, lane0);
    }
    if (b < NFFN) {
      const uint32_t own = base + unit_of(FT_G, warp >> 1) + (warp & 1) * 8192;
      mbar_wait(bar_box + (4 + (warp >> 1)) * 8, 0);
      LOAD_WF(1);
      uint32_t* const ydst = ypart_slot(b, warp * 16 + (tq & 1) * 8 + g);
      PROF(8, ct == PT, 31); STAMP(10);
      bool wdok;
      {
        uint32_t n = 0;
        while (!(wdok = __all_sync(0xffffffffu, mbar_test(bar_box + (8 + (warp >> 1)) * 8, 0))) && !__all_sync(0xffffffffu, mbar_test(bar_sel, 0))) watchdog(n);
      }
      if (wdok) {
#pragma unroll
        for (int f = 0; f < 16; f++) LOAD_WD(f);
      }
      STAMP(11);
      mbar_wait(bar_sel, 0);
      PROF(8, ct == PT, 33); STAMP(12);
      float d[8][4];
#pragma unroll
      for (int i = 0; i < 4; i++) { d[i][0] = 0.f; d[i][1] = 0.f; d[i][2] = 0.f; d[i][3] = 0.f; }
#pragma unroll
      for (int ks = 0; ks < 8; ks++) {
        const uint2 hb = lds2(own + 256 + ks * 32 + tq * 8);
#pragma unroll
        for (int mt = 0; mt < 4; mt++) {
          const int r = ks * 16 + mt * 4;
          mma16816(d[mt], wf[r], wf[r + 1], wf[r + 2], wf[r + 3], hb.x, hb.y);
        }
      }
      sts2(own + (tq * 8 + g) * 8, __float_as_uint((tq & 2) ? ((tq & 1) ? d[1][2] : d[1][0]) : ((tq & 1) ? d[0][2] : d[0][0])),
           __float_as_uint((tq & 2) ? ((tq & 1) ? d[3][2] : d[3][0]) : ((tq & 1) ? d[2][2] : d[2][0])));
      bar_sync(1, 256);
      uint32_t ab[4];
      {
        float G = 0.f, U = 0.f;
        uint2 pv[8];
#pragma unroll
        for (int w8 = 0; w8 < 8; w8++) pv[w8] = lds2(base + ln * 8 + ((FT_G >> (w8 >> 1) * 4) & 15) * UNIT + (w8 & 1) * 8192);
#pragma unroll
        for (int w8 = 0; w8 < 8; w8 += 2) {
          G += __uint_as_float(pv[w8].x) + __uint_as_float(pv[w8 + 1].x);
          U += __uint_as_float(pv[w8].y) + __uint_as_float(pv[w8 + 1].y);
        }
        const float act = rbf(silu_f(rbf(G))) * rbf(U);
        const uint32_t pk = pack_bf(act, __shfl_down_sync(0xffffffffu, act, 1));
#pragma unroll
        for (int i = 0; i < 4; i++) ab[i] = __shfl_sync(0xffffffffu, pk, i * 8 + tq * 2);
      }
      if (!wdok) {
        mbar_wait(bar_box + (8 + (warp >> 1)) * 8, 0);
#pragma unroll
        for (int f = 0; f < 16; f++) LOAD_WD(f);
      }
      PROF(8, ct == PT, 34); STAMP(13);
#pragma unroll
      for (int mt = 0; mt < 8; mt++) {
        d[mt][0] = 0.f; d[mt][1] = 0.f; d[mt][2] = 0.f; d[mt][3] = 0.f;
        mma16816(d[mt], wd[mt * 8], wd[mt * 8 + 1], wd[mt * 8 + 2], wd[mt * 8 + 3], ab[0], ab[1]);
        mma16816(d[mt], wd[mt * 8 + 4], wd[mt * 8 + 5], wd[mt * 8 + 6], wd[mt * 8 + 7], ab[2], ab[3]);
      }
      uint32_t yw[4];
#pragma unroll
      for (int i = 0; i < 4; i++) yw[i] = (tq & 1) ? pack_bf(d[2 * i][2], d[2 * i + 1][2]) : pack_bf(d[2 * i][0], d[2 * i + 1][0]);
      if (tq < 2) st_b128(ydst, (yw[0] & ~1u) | (tag & 1), (yw[1] & ~1u) | (tag >> 1), yw[2], yw[3]);
      PROF(8, ct == PT, 35); STAMP(14);
    }
    mbar_wait(bar_sel, 0);
    mbar_arrive_pred(bar_win, ct == 0);
    const int iwin = lds1(par + PAR_CONST + 60) & 0x7ff;
    const bool cand = (iwin >> 4) == rb * 8 + warp;
    {
      const uint32_t mm0 = __shfl_sync(0xffffffffu, mm, ln & ~1), mm1 = __shfl_sync(0xffffffffu, mm, ln | 1);
      const uint32_t ih0 = __shfl_sync(0xffffffffu, ih, ln & ~1), ih1 = __shfl_sync(0xffffffffu, ih, ln | 1);
      const uint32_t il0 = __shfl_sync(0xffffffffu, il, ln & ~1), il1 = __shfl_sync(0xffffffffu, il, ln | 1);
#pragma unroll OUR
      for (int hf = 0; hf < 2; hf++) {
        uint32_t x[16];
#pragma unroll
        for (int i = 0; i < 8; i += 2) ldmatrix4((trow ^ (i << 4)) + hf * 16384, x[2 * i], x[2 * i + 1], x[2 * i + 2], x[2 * i + 3]);
#pragma unroll
        for (int i = 0; i < 8; i++) {
          const uint4 pv = lds4(par + PAR_T2 + (hf * 8 + i) * 64 + tq * 16);
          x[2 * i] = hfma2(hfma2(ln_norm(x[2 * i], mm0, ih0, il0), pv.x, pv.y), pv.z, x[2 * i]);
          x[2 * i + 1] = hfma2(hfma2(ln_norm(x[2 * i + 1], mm1, ih1, il1), pv.x, pv.y), pv.z, x[2 * i + 1]);
        }
#pragma unroll
        for (int i = 0; i < 8; i += 2) stmatrix4((trow ^ (i << 4)) + hf * 16384, x[2 * i], x[2 * i + 1], x[2 * i + 2], x[2 * i + 3]);
        if (!cand) fence_async_smem();
        __syncwarp();
        if (!cand && elect_one()) {
          tma2d_store(&maps.out, res + hf * 16384 + warp * 2048, cj * 128 + hf * 64, rb * 128 + warp * 16);
          asm volatile("cp.async.bulk.commit_group;" ::: "memory");
        }
      }
    }
    if (cand) {
      const int wrow0 = warp * 16;
#pragma unroll 2
      for (int p = 0; p < 8; p++) {
        const int row = 2 * p + (ln >> 4), ch = ln & 15;
        const uint4 v = lds4(res + (ch >> 3) * 16384 + (wrow0 + row) * 128 + (((ch & 7) ^ (row & 7)) << 4));
        if (rb * 128 + wrow0 + row != iwin) *reinterpret_cast<uint4*>(P.out + (size_t)(rb * 128 + wrow0 + row) * DM + cj * 128 + ch * 8) = v;
      }
    }
    asm volatile("cp.async.bulk.wait_group.read 0;" ::: "memory");
    PROF(8, ct == PT, 11); STAMP(15);
    cluster_wait();
  }
}

typedef CUresult (*EncodeFn)(CUtensorMap*, CUtensorMapDataType, cuuint32_t, void*, const cuuint64_t*, const cuuint64_t*,
                             const cuuint32_t*, const cuuint32_t*, CUtensorMapInterleave, CUtensorMapSwizzle,
                             CUtensorMapL2promotion, CUtensorMapFloatOOBfill);

void map2d(EncodeFn enc, CUtensorMap* m, const void* p, uint64_t rows, uint64_t cols, uint32_t brows) {
  cuuint64_t dims[2] = {cols, rows}, strides[1] = {cols * 2};
  cuuint32_t box[2] = {64, brows}, es[2] = {1, 1};
  enc(m, CU_TENSOR_MAP_DATA_TYPE_BFLOAT16, 2, const_cast<void*>(p), dims, strides, box, es, CU_TENSOR_MAP_INTERLEAVE_NONE,
      CU_TENSOR_MAP_SWIZZLE_128B, CU_TENSOR_MAP_L2_PROMOTION_L2_256B, CU_TENSOR_MAP_FLOAT_OOB_FILL_NONE);
}
void map2d_narrow(EncodeFn enc, CUtensorMap* m, const void* p, uint64_t rows, uint64_t cols, uint32_t brows) {
  cuuint64_t dims[2] = {cols, rows}, strides[1] = {cols * 2};
  cuuint32_t box[2] = {32, brows}, es[2] = {1, 1};
  enc(m, CU_TENSOR_MAP_DATA_TYPE_BFLOAT16, 2, const_cast<void*>(p), dims, strides, box, es, CU_TENSOR_MAP_INTERLEAVE_NONE,
      CU_TENSOR_MAP_SWIZZLE_64B, CU_TENSOR_MAP_L2_PROMOTION_L2_64B, CU_TENSOR_MAP_FLOAT_OOB_FILL_NONE);
}
void map3d(EncodeFn enc, CUtensorMap* m, const void* p, uint64_t rows, uint64_t cols, uint32_t brows, uint32_t nch) {
  cuuint64_t dims[3] = {64, rows, cols / 64}, strides[2] = {cols * 2, 128};
  cuuint32_t box[3] = {64, brows, nch}, es[3] = {1, 1, 1};
  enc(m, CU_TENSOR_MAP_DATA_TYPE_BFLOAT16, 3, const_cast<void*>(p), dims, strides, box, es, CU_TENSOR_MAP_INTERLEAVE_NONE,
      CU_TENSOR_MAP_SWIZZLE_128B, CU_TENSOR_MAP_L2_PROMOTION_L2_256B, CU_TENSOR_MAP_FLOAT_OOB_FILL_NONE);
}

}

extern "C" void kernel_launch(void* const* d_in, const int* in_sizes, int n_in, void* d_out, int out_size) {
  (void)in_sizes; (void)n_in; (void)out_size;
  static EncodeFn enc = nullptr;
  if (!enc) {
    void* fn = nullptr;
    cudaDriverEntryPointQueryResult st;
    cudaGetDriverEntryPoint("cuTensorMapEncodeTiled", &fn, cudaEnableDefault, &st);
    enc = (EncodeFn)fn;
    cudaFuncSetAttribute(fused_kernel, cudaFuncAttributeMaxDynamicSharedMemorySize, SMEM_BYTES);
  }
  Maps maps;
  map2d(enc, &maps.x, d_in[0], SEQ, DM, 128);
  map2d(enc, &maps.out, d_out, SEQ, DM, 16);
  map3d(enc, &maps.wq, d_in[3], DM, NQ, 64, 2);
  map3d(enc, &maps.k, d_in[1], 4 * SK, 128, 128, 1);
  map3d(enc, &maps.v, d_in[2], 4 * SK, 128, 128, 1);
  map3d(enc, &maps.wo, d_in[4], NQ, DM, 64, 2);
  map2d_narrow(enc, &maps.wg, d_in[7], DM, FF, 256);
  map2d_narrow(enc, &maps.wu, d_in[8], DM, FF, 256);
  map3d(enc, &maps.wd, d_in[9], FF, DM, 32, 4);
  map2d_narrow(enc, &maps.wm, d_in[11], DM, NMOD, 256);
  Ptrs p;
  p.x = (const __nv_bfloat16*)d_in[0];
  p.w_r = (const __nv_bfloat16*)d_in[6];
  p.w_gate = (const __nv_bfloat16*)d_in[7];
  p.w_up = (const __nv_bfloat16*)d_in[8];
  p.w_down = (const __nv_bfloat16*)d_in[9];
  p.c = (const __nv_bfloat16*)d_in[10];
  p.w_mod = (const __nv_bfloat16*)d_in[11];
  p.out = (__nv_bfloat16*)d_out;
  fused_kernel<<<NMAIN + NHELP, 384, SMEM_BYTES>>>(maps, p);
}
```

```cpp
#include <cuda_runtime.h>
#include <cuda_bf16.h>
#include <cuda.h>
#include <stdint.h>
#include <type_traits>

#define HD 2
#define HDX 2
#define NRS 8
#define FPACE 3
#define GOST 20
#define WB 2
#define WN 20
#define RES0 17
#define RES1 20
#define HU 32
#define NS1 5
#define PG0 15
#define FB0 0
#define FB2 8
#define OPS 8192
#define OFL 0
#define ODS 8
#define MODUL hfma2
#define ODS1 5
#define LD1 0
#define LD2 4
#define FB1 2
#define FPB 8
#define FPACE0 2
#define OSL 900
#define OSL2 400
#define CR 8
#define CS 8
#define OURV 1
#define VREL 5
#define E0 3

namespace {

constexpr int SEQ = 2048, DM = 1024, NQ = 4096, SK = 2048, WIN = 512, FF = 3584, NMOD = 6144;
constexpr int OUR = OURV;
constexpr int NMAIN = 128, NHELP = 4, NFFN = 112;
constexpr int NSLOT = 4, SLOT_BYTES = 32768, UNIT = 16384, GST_BYTES = 3 * UNIT;
constexpr uint32_t XT1 = 0xDCBA, XT2 = 0x9687, XT2B = 0x96DC;
constexpr uint32_t WT0 = 0xA741, WT1 = 0x7420, WT2 = 0x4A20;
constexpr uint32_t AT0 = WT1, AT1 = WT2;
constexpr uint32_t QT = 0xDC9696DC;
constexpr int OFF_STAGE = 12 * UNIT;
constexpr uint32_t FT_G = 0x07B3, FT_U = 0xA628, FT_D = 0x5149;
constexpr int OFF_RES = 12 * UNIT;
constexpr int OFF_PAR = 14 * UNIT;
constexpr int OFF_BAR = OFF_PAR + 2528;
constexpr int SMEM_BYTES = OFF_BAR + 544;
static_assert(SMEM_BYTES <= 232448, "smem");

constexpr int PAR_T1 = 0;
constexpr int PAR_T2 = 512;
constexpr int PAR_CONST = 1536;
constexpr int PAR_RED = 1600;
constexpr int PAR_SINK = 2176;

struct Maps {
  CUtensorMap x, wq, k, v, wo, wg, wu, wd, wm, out;
};
struct Ptrs {
  const __nv_bfloat16 *x, *w_r, *c, *w_mod, *w_gate, *w_up, *w_down;
  __nv_bfloat16* out;
};

__device__ __align__(1024) uint8_t g_act[16 * 80 * UNIT];
__device__ __align__(128) uint32_t g_mod[NMOD];
__device__ __align__(128) uint32_t g_modp[2 * 2 * DM];
__device__ __align__(128) uint32_t g_ln1[SEQ * 4];
__device__ __align__(128) uint32_t g_cnt_h[16 * 32];
__device__ __align__(128) uint32_t g_cnt_o[128 * 32];
__device__ __align__(128) uint32_t g_xch[NMAIN * 8 * 256 * 4];
__device__ __align__(128) uint32_t g_stats[8 * SEQ * 4];
__device__ __align__(128) uint32_t g_cand[CR * 512];
__device__ __align__(128) uint32_t g_row[16 * 2 * DM];
__device__ __align__(128) uint32_t g_ypart[NMAIN * NFFN * 4];
__device__ __forceinline__ uint32_t* ypart_slot(int writer, int reader) { return g_ypart + (writer * NMAIN + reader) * 4; }
__device__ uint32_t g_epoch;

__device__ __forceinline__ uint32_t fresh_lane() { uint32_t l; asm volatile("mov.u32 %0, %%laneid;" : "=r"(l)); return l; }
__device__ __forceinline__ uint32_t frag_offset(int warp) {
  const uint32_t l = fresh_lane();
  return ((warp & 3) * 16 + (l & 15)) * 128 + (((l >> 4) ^ (l & 7)) << 4);
}
__device__ __forceinline__ bool elect_one() {
  uint32_t p;
  asm volatile("{ .reg .pred q; elect.sync _|q, 0xffffffff; selp.u32 %0, 1, 0, q; }" : "=r"(p));
  return p;
}
__device__ __forceinline__ uint32_t smem_u32(const void* p) { return (uint32_t)__cvta_generic_to_shared(p); }
__device__ __forceinline__ void mbar_init(uint32_t bar, uint32_t cnt) {
  asm volatile("mbarrier.init.shared::cta.b64 [%0], %1;" ::"r"(bar), "r"(cnt) : "memory");
}
__device__ __forceinline__ void mbar_expect_tx(uint32_t bar, uint32_t bytes) {
  asm volatile("mbarrier.arrive.expect_tx.shared::cta.b64 _, [%0], %1;" ::"r"(bar), "r"(bytes) : "memory");
}
__device__ __forceinline__ void mbar_arrive(uint32_t bar) {
  asm volatile("mbarrier.arrive.shared::cta.b64 _, [%0];" ::"r"(bar) : "memory");
}
__device__ __forceinline__ void mbar_arrive_pred(uint32_t bar, bool p) {
  asm volatile("{ .reg .pred p; setp.ne.b32 p, %1, 0; @p mbarrier.arrive.shared::cta.b64 _, [%0]; }" ::"r"(bar), "r"((int)p) : "memory");
}
__device__ __forceinline__ void mbar_arrive_cl(uint32_t bar, uint32_t off, bool p = true) {
  asm volatile("{ .reg .pred p, q; .reg .b32 a; setp.ne.b32 q, %2, 0; setp.ne.and.b32 p, %0, 0, q; add.u32 a, %0, %1; @p mbarrier.arrive.shared::cluster.b64 _, [a]; }"
               ::"r"(bar), "r"(off), "r"((int)p) : "memory");
}
__device__ __forceinline__ uint32_t mapa(uint32_t addr, uint32_t cta) {
  uint32_t r; asm("mapa.shared::cluster.u32 %0, %1, %2;" : "=r"(r) : "r"(addr), "r"(cta)); return r;
}
__device__ __forceinline__ void cluster_arrive() { asm volatile("barrier.cluster.arrive.relaxed.aligned;" ::: "memory"); }
__device__ __forceinline__ void cluster_wait() { asm volatile("barrier.cluster.wait.aligned;" ::: "memory"); }
__device__ __forceinline__ void watchdog(uint32_t& n) {
}
__device__ __forceinline__ void mbar_wait(uint32_t bar, uint32_t parity) {
  asm volatile("{\n.reg .pred p;\nWAIT_%=:\nmbarrier.try_wait.parity.shared::cta.b64 p, [%0], %1;\n@!p bra WAIT_%=;\n}" ::"r"(bar), "r"(parity) : "memory");
}
__device__ __forceinline__ bool mbar_test(uint32_t bar, uint32_t parity) {
  uint32_t ok;
  asm volatile("{\n.reg .pred p;\nmbarrier.test_wait.parity.shared::cta.b64 p, [%1], %2;\nselp.u32 %0, 1, 0, p;\n}" : "=r"(ok) : "r"(bar), "r"(parity) : "memory");
  return ok;
}
__device__ __forceinline__ uint64_t l2_stream() {
  uint64_t f; asm("createpolicy.fractional.L2::evict_first.b64 %0, 1.0;" : "=l"(f)); return f;
}
__device__ __forceinline__ void tma2d(uint32_t dst, const CUtensorMap* m, int c0, int c1, uint32_t bar) {
  asm volatile("cp.async.bulk.tensor.2d.shared::cluster.global.mbarrier::complete_tx::bytes.L2::cache_hint [%0], [%1, {%3, %4}], [%2], %5;"
               ::"r"(dst), "l"(m), "r"(bar), "r"(c0), "r"(c1), "l"(l2_stream()) : "memory");
}
__device__ __forceinline__ void bulk_load(uint32_t dst, const void* src, uint32_t bytes, uint32_t bar) {
  asm volatile("cp.async.bulk.shared::cluster.global.mbarrier::complete_tx::bytes [%0], [%1], %2, [%3];" ::"r"(dst), "l"(src), "r"(bytes), "r"(bar) : "memory");
}
__device__ __forceinline__ void bulk_load_stream(uint32_t dst, const void* src, uint32_t bytes, uint32_t bar) {
  asm volatile("cp.async.bulk.shared::cluster.global.mbarrier::complete_tx::bytes.L2::cache_hint [%0], [%1], %2, [%3], %4;"
               ::"r"(dst), "l"(src), "r"(bytes), "r"(bar), "l"(l2_stream()) : "memory");
}
__device__ __forceinline__ void tma2d_store(const CUtensorMap* m, uint32_t src, int c0, int c1) {
  asm volatile("cp.async.bulk.tensor.2d.global.shared::cta.bulk_group [%0, {%2, %3}], [%1];" ::"l"(m), "r"(src), "r"(c0), "r"(c1) : "memory");
}
__device__ __forceinline__ void bulk_store(void* dst, uint32_t src, uint32_t bytes) {
  asm volatile("cp.async.bulk.global.shared::cta.bulk_group [%0], [%1], %2;" ::"l"(dst), "r"(src), "r"(bytes) : "memory");
}
__device__ __forceinline__ int slice_of(int i) { return i + ((i & 7) == 1) - ((i & 7) == 2); }
__device__ __forceinline__ int otile_of(int i, int cj) {
  const int h = (0xFB7EA6D951C84320ull >> (i >> 1) * 4) & 15;
  return ((cj ^ (h >> 2) * 2) * 4 + (h & 3)) * 2 + (i & 1);
}
__device__ __forceinline__ uint32_t unit_of(uint32_t table, uint32_t i) { return ((table >> (i * 4)) & 15) * UNIT; }
__device__ __forceinline__ void tma3d(uint32_t dst, const CUtensorMap* m, int c0, int c1, int c2, uint32_t bar) {
  asm volatile("cp.async.bulk.tensor.3d.shared::cluster.global.mbarrier::complete_tx::bytes.L2::cache_hint [%0], [%1, {%3, %4, %5}], [%2], %6;"
               ::"r"(dst), "l"(m), "r"(bar), "r"(c0), "r"(c1), "r"(c2), "l"(l2_stream()) : "memory");
}
template <bool STREAM>
__device__ __forceinline__ void tma3d_mc(uint32_t dst, const CUtensorMap* m, int c0, int c1, int c2, uint32_t bar) {
  if (STREAM)
    asm volatile("cp.async.bulk.tensor.3d.shared::cluster.global.mbarrier::complete_tx::bytes.multicast::cluster.L2::cache_hint [%0], [%1, {%3, %4, %5}], [%2], %6, %7;"
                 ::"r"(dst), "l"(m), "r"(bar), "r"(c0), "r"(c1), "r"(c2), "h"((uint16_t)3), "l"(l2_stream()) : "memory");
  else
    asm volatile("cp.async.bulk.tensor.3d.shared::cluster.global.mbarrier::complete_tx::bytes.multicast::cluster [%0], [%1, {%3, %4, %5}], [%2], %6;"
                 ::"r"(dst), "l"(m), "r"(bar), "r"(c0), "r"(c1), "r"(c2), "h"((uint16_t)3) : "memory");
}
__device__ __forceinline__ void prefetch_map(const CUtensorMap* m) {
  asm volatile("prefetch.tensormap [%0];" ::"l"(m) : "memory");
}
__device__ __forceinline__ void fence_async() { asm volatile("fence.proxy.async.global;" ::: "memory"); }
__device__ __forceinline__ void fence_async_smem() { asm volatile("fence.proxy.async.shared::cta;" ::: "memory"); }
__device__ __forceinline__ void bar_sync(int id, int n) { asm volatile("bar.sync %0, %1;" ::"r"(id), "r"(n) : "memory"); }
__device__ __forceinline__ void bar_arrive(int id, int n) { asm volatile("bar.arrive %0, %1;" ::"r"(id), "r"(n) : "memory"); }
__device__ __forceinline__ void wg_fence() { asm volatile("wgmma.fence.sync.aligned;" ::: "memory"); }
__device__ __forceinline__ void wg_commit() { asm volatile("wgmma.commit_group.sync.aligned;" ::: "memory"); }
template <int N> __device__ __forceinline__ void wg_wait() { asm volatile("wgmma.wait_group.sync.aligned %0;" ::"n"(N) : "memory"); }
__device__ __forceinline__ uint64_t make_desc(uint32_t addr, uint32_t lbo, uint32_t sbo) {
  return (uint64_t)((addr & 0x3FFFF) >> 4) | ((uint64_t)(lbo >> 4) << 16) | ((uint64_t)(sbo >> 4) << 32) | (1ull << 62);
}
__device__ __forceinline__ uint32_t ld_relaxed(const uint32_t* p) {
  uint32_t v; asm volatile("ld.relaxed.gpu.global.u32 %0, [%1];" : "=r"(v) : "l"(p) : "memory"); return v;
}
__device__ __forceinline__ uint32_t ld_acquire(const uint32_t* p) {
  uint32_t v; asm volatile("ld.acquire.gpu.global.u32 %0, [%1];" : "=r"(v) : "l"(p) : "memory"); return v;
}
__device__ __forceinline__ uint4 ld_relaxed4(const uint32_t* p) {
  uint4 v; asm volatile("ld.relaxed.gpu.global.v4.u32 {%0,%1,%2,%3}, [%4];" : "=r"(v.x), "=r"(v.y), "=r"(v.z), "=r"(v.w) : "l"(p) : "memory"); return v;
}
__device__ __forceinline__ uint2 ld_relaxed2(const uint32_t* p) {
  uint2 v; asm volatile("ld.relaxed.gpu.global.v2.u32 {%0,%1}, [%2];" : "=r"(v.x), "=r"(v.y) : "l"(p) : "memory"); return v;
}
__device__ __forceinline__ void st_relaxed(uint32_t* p, uint32_t v) {
  asm volatile("st.relaxed.gpu.global.u32 [%0], %1;" ::"l"(p), "r"(v) : "memory");
}
__device__ __forceinline__ void st_relaxed2(uint32_t* p, uint32_t a, uint32_t b) {
  asm volatile("st.relaxed.gpu.global.v2.u32 [%0], {%1,%2};" ::"l"(p), "r"(a), "r"(b) : "memory");
}
__device__ __forceinline__ void st_relaxed4(uint32_t* p, uint32_t a, uint32_t b, uint32_t c, uint32_t d) {
  asm volatile("st.relaxed.gpu.global.v4.u32 [%0], {%1,%2,%3,%4};" ::"l"(p), "r"(a), "r"(b), "r"(c), "r"(d) : "memory");
}
__device__ __forceinline__ void st_b128(uint32_t* p, uint32_t a, uint32_t b, uint32_t c, uint32_t d) {
  asm volatile("{ .reg .b64 u, v; .reg .b128 w; mov.b64 u, {%1, %2}; mov.b64 v, {%3, %4}; mov.b128 w, {u, v}; st.relaxed.gpu.global.b128 [%0], w; }"
               ::"l"(p), "r"(a), "r"(b), "r"(c), "r"(d) : "memory");
}
__device__ __forceinline__ uint4 ld_b128(const uint32_t* p) {
  uint4 r;
  asm volatile("{ .reg .b64 u, v; .reg .b128 w; ld.relaxed.gpu.global.b128 w, [%4]; mov.b128 {u, v}, w; mov.b64 {%0, %1}, u; mov.b64 {%2, %3}, v; }"
               : "=r"(r.x), "=r"(r.y), "=r"(r.z), "=r"(r.w) : "l"(p) : "memory");
  return r;
}
__device__ __forceinline__ void st_pairs(uint32_t* p, uint32_t a, uint32_t b, uint32_t tag) {
  asm volatile("{ .reg .b64 u, v; mov.b64 u, {%1, %3}; mov.b64 v, {%2, %3}; st.relaxed.gpu.global.v2.b64 [%0], {u, v}; }"
               ::"l"(p), "r"(a), "r"(b), "r"(tag) : "memory");
}
__device__ __forceinline__ uint4 ld_pairs(const uint32_t* p) {
  uint4 v;
  asm volatile("{ .reg .b64 u, v; ld.relaxed.gpu.global.v2.b64 {u, v}, [%4]; mov.b64 {%0, %1}, u; mov.b64 {%2, %3}, v; }"
               : "=r"(v.x), "=r"(v.y), "=r"(v.z), "=r"(v.w) : "l"(p) : "memory");
  return v;
}
__device__ __forceinline__ uint2 ld_pair(const uint32_t* p) {
  uint2 v;
  asm volatile("{ .reg .b64 u; ld.relaxed.gpu.global.b64 u, [%2]; mov.b64 {%0, %1}, u; }" : "=r"(v.x), "=r"(v.y) : "l"(p) : "memory");
  return v;
}
__device__ __forceinline__ void red_release(uint32_t* p, uint32_t v) {
  asm volatile("red.release.gpu.global.add.u32 [%0], %1;" ::"l"(p), "r"(v) : "memory");
}
__device__ __forceinline__ uint32_t ldg_nc1(const void* p) {
  uint32_t v;
  asm volatile("ld.global.nc.u32 %0, [%1];" : "=r"(v) : "l"(p));
  return v;
}
__device__ __forceinline__ uint4 ldg_nc4(const void* p) {
  uint4 v; asm volatile("ld.global.nc.L1::no_allocate.v4.u32 {%0,%1,%2,%3}, [%4];" : "=r"(v.x), "=r"(v.y), "=r"(v.z), "=r"(v.w) : "l"(p)); return v;
}
__device__ __forceinline__ uint4 ldg_stream4(const void* p) {
  uint4 v;
  asm volatile("ld.global.nc.L1::no_allocate.L2::cache_hint.v4.u32 {%0,%1,%2,%3}, [%4], %5;" : "=r"(v.x), "=r"(v.y), "=r"(v.z), "=r"(v.w) : "l"(p), "l"(l2_stream()));
  return v;
}
__device__ __forceinline__ void stg4(void* p, uint4 v) {
  asm volatile("st.global.v4.u32 [%0], {%1,%2,%3,%4};" ::"l"(p), "r"(v.x), "r"(v.y), "r"(v.z), "r"(v.w) : "memory");
}
__device__ __forceinline__ void wait_counter(const uint32_t* p, uint32_t target) {
  uint32_t n = 0;
  while (__any_sync(0xffffffffu, (int)(ld_acquire(p) - target) < 0)) { watchdog(n); }
}
__device__ __forceinline__ uint32_t tagf(float v, uint32_t tag) { return (__float_as_uint(v) & ~3u) | tag; }
__device__ __forceinline__ bool tag_ok(uint4 v, uint32_t tag) { return (((v.x ^ tag) | (v.y ^ tag) | (v.z ^ tag) | (v.w ^ tag)) & 3u) == 0; }
__device__ __forceinline__ float untag_sum(uint32_t a, uint32_t b) { return __uint_as_float(a & ~3u) + __uint_as_float(b & ~3u); }
__device__ __forceinline__ uint4 poll4(const uint32_t* p, uint32_t tag) {
  uint4 v = ld_relaxed4(p);
  uint32_t n = 0;
  while (!__all_sync(0xffffffffu, tag_ok(v, tag))) { v = ld_relaxed4(p); watchdog(n); }
  return v;
}
__device__ __forceinline__ float bf_lo(uint32_t v) { return __uint_as_float(v << 16); }
__device__ __forceinline__ float bf_hi(uint32_t v) { return __uint_as_float(v & 0xffff0000u); }
__device__ __forceinline__ uint32_t pack_bf(float lo, float hi) {
  uint32_t r; asm("cvt.rn.bf16x2.f32 %0, %1, %2;" : "=r"(r) : "f"(hi), "f"(lo)); return r;
}
__device__ __forceinline__ float rbf(float v) { return __uint_as_float(pack_bf(0.f, v) & 0xffff0000u); }
__device__ __forceinline__ uint32_t hmul2(uint32_t a, uint32_t b) {
  uint32_t r; asm("mul.rn.bf16x2 %0, %1, %2;" : "=r"(r) : "r"(a), "r"(b)); return r;
}
__device__ __forceinline__ uint32_t hadd2(uint32_t a, uint32_t b) {
  uint32_t r; asm("add.rn.bf16x2 %0, %1, %2;" : "=r"(r) : "r"(a), "r"(b)); return r;
}
__device__ __forceinline__ uint32_t hsub2(uint32_t a, uint32_t b) {
  uint32_t r; asm("sub.rn.bf16x2 %0, %1, %2;" : "=r"(r) : "r"(a), "r"(b)); return r;
}
__device__ __forceinline__ uint32_t hmax2(uint32_t a, uint32_t b) {
  uint32_t r; asm("max.bf16x2 %0, %1, %2;" : "=r"(r) : "r"(a), "r"(b)); return r;
}
__device__ __forceinline__ float rcp(float x) { float r; asm("rcp.approx.ftz.f32 %0, %1;" : "=f"(r) : "f"(x)); return r; }
__device__ __forceinline__ float ex2(float x) { float r; asm("ex2.approx.ftz.f32 %0, %1;" : "=f"(r) : "f"(x)); return r; }
__device__ __forceinline__ void stmatrix4(uint32_t addr, uint32_t a, uint32_t b, uint32_t c, uint32_t d) {
  asm volatile("stmatrix.sync.aligned.m8n8.x4.shared.b16 [%0], {%1,%2,%3,%4};" ::"r"(addr), "r"(a), "r"(b), "r"(c), "r"(d) : "memory");
}
__device__ __forceinline__ void ldmatrix4(uint32_t addr, uint32_t& a, uint32_t& b, uint32_t& c, uint32_t& d) {
  asm volatile("ldmatrix.sync.aligned.m8n8.x4.shared.b16 {%0,%1,%2,%3}, [%4];" : "=r"(a), "=r"(b), "=r"(c), "=r"(d) : "r"(addr) : "memory");
}
__device__ __forceinline__ void ldmatrix4t(uint32_t addr, uint32_t& a, uint32_t& b, uint32_t& c, uint32_t& d) {
  asm volatile("ldmatrix.sync.aligned.m8n8.x4.trans.shared.b16 {%0,%1,%2,%3}, [%4];" : "=r"(a), "=r"(b), "=r"(c), "=r"(d) : "r"(addr) : "memory");
}
__device__ __forceinline__ void mma16816(float (&d)[4], uint32_t a0, uint32_t a1, uint32_t a2, uint32_t a3, uint32_t b0, uint32_t b1) {
  asm volatile("mma.sync.aligned.m16n8k16.row.col.f32.bf16.bf16.f32 {%0,%1,%2,%3}, {%4,%5,%6,%7}, {%8,%9}, {%0,%1,%2,%3};"
               : "+f"(d[0]), "+f"(d[1]), "+f"(d[2]), "+f"(d[3]) : "r"(a0), "r"(a1), "r"(a2), "r"(a3), "r"(b0), "r"(b1));
}
__device__ __forceinline__ void sts1(uint32_t a, uint32_t v) { asm volatile("st.shared.u32 [%0], %1;" ::"r"(a), "r"(v) : "memory"); }
__device__ __forceinline__ uint4 lds4(uint32_t a) {
  uint4 v; asm volatile("ld.shared.v4.u32 {%0,%1,%2,%3}, [%4];" : "=r"(v.x), "=r"(v.y), "=r"(v.z), "=r"(v.w) : "r"(a) : "memory"); return v;
}
__device__ __forceinline__ uint2 lds2(uint32_t a) {
  uint2 v; asm volatile("ld.shared.v2.u32 {%0,%1}, [%2];" : "=r"(v.x), "=r"(v.y) : "r"(a) : "memory"); return v;
}
__device__ __forceinline__ uint32_t lds1(uint32_t a) {
  uint32_t v; asm volatile("ld.shared.u32 %0, [%1];" : "=r"(v) : "r"(a) : "memory"); return v;
}
__device__ __forceinline__ void sts2(uint32_t a, uint32_t x, uint32_t y) { asm volatile("st.shared.v2.u32 [%0], {%1,%2};" ::"r"(a), "r"(x), "r"(y) : "memory"); }
__device__ __forceinline__ void sts4(uint32_t a, uint4 v) {
  asm volatile("st.shared.v4.u32 [%0], {%1,%2,%3,%4};" ::"r"(a), "r"(v.x), "r"(v.y), "r"(v.z), "r"(v.w) : "memory");
}
__device__ __forceinline__ float silu_f(float v) { return __fdividef(v, 1.f + __expf(-v)); }
__device__ __forceinline__ uint32_t hfma2(uint32_t a, uint32_t b, uint32_t c) {
  uint32_t r; asm("fma.rn.bf16x2 %0, %1, %2, %3;" : "=r"(r) : "r"(a), "r"(b), "r"(c)); return r;
}
__device__ __forceinline__ void split_inv(float sd, uint32_t& ih, uint32_t& il) {
  const float inv = rcp(sd);
  ih = pack_bf(inv, inv);
  const float lo = inv - bf_lo(ih);
  il = pack_bf(lo, lo);
}
__device__ __forceinline__ uint32_t ln_norm(uint32_t x, uint32_t mean2, uint32_t ih, uint32_t il) {
  const uint32_t d = hsub2(x, mean2);
  return hfma2(d, ih, hmul2(d, il));
}
__device__ __forceinline__ uint32_t modul(uint32_t n, uint32_t c1, uint32_t sh) { return hadd2(hmul2(n, c1), sh); }
__device__ __forceinline__ uint32_t ln_mod(uint32_t x, uint32_t mean2, uint32_t ih, uint32_t il, uint32_t c1, uint32_t sh) {
  return modul(ln_norm(x, mean2, ih, il), c1, sh);
}

#define R8(a, i) "+f"(a[i]), "+f"(a[i + 1]), "+f"(a[i + 2]), "+f"(a[i + 3]), "+f"(a[i + 4]), "+f"(a[i + 5]), "+f"(a[i + 6]), "+f"(a[i + 7])
#define D64 "{%0,%1,%2,%3,%4,%5,%6,%7,%8,%9,%10,%11,%12,%13,%14,%15,%16,%17,%18,%19,%20,%21,%22,%23,%24,%25,%26,%27,%28,%29,%30,%31," \
            "%32,%33,%34,%35,%36,%37,%38,%39,%40,%41,%42,%43,%44,%45,%46,%47,%48,%49,%50,%51,%52,%53,%54,%55,%56,%57,%58,%59,%60,%61,%62,%63}"
template <int TB>
__device__ __forceinline__ void mma_ss(float (&d)[64], uint64_t da, uint64_t db, int sc) {
  asm volatile("{\n.reg .pred p;\nsetp.ne.b32 p, %66, 0;\n"
               "wgmma.mma_async.sync.aligned.m64n128k16.f32.bf16.bf16 " D64 ", %64, %65, p, 1, 1, 0, %67;\n}"
               : R8(d, 0), R8(d, 8), R8(d, 16), R8(d, 24), R8(d, 32), R8(d, 40), R8(d, 48), R8(d, 56)
               : "l"(da), "l"(db), "r"(sc), "n"(TB));
}
template <int TB>
__device__ __forceinline__ void mma_rs(float (&d)[64], uint32_t a0, uint32_t a1, uint32_t a2, uint32_t a3, uint64_t db, int sc) {
  asm volatile("{\n.reg .pred p;\nsetp.ne.b32 p, %69, 0;\n"
               "wgmma.mma_async.sync.aligned.m64n128k16.f32.bf16.bf16 " D64 ", {%64,%65,%66,%67}, %68, p, 1, 1, %70;\n}"
               : R8(d, 0), R8(d, 8), R8(d, 16), R8(d, 24), R8(d, 32), R8(d, 40), R8(d, 48), R8(d, 56)
               : "r"(a0), "r"(a1), "r"(a2), "r"(a3), "l"(db), "r"(sc), "n"(TB));
}
#define D128 "{%0,%1,%2,%3,%4,%5,%6,%7,%8,%9,%10,%11,%12,%13,%14,%15,%16,%17,%18,%19,%20,%21,%22,%23,%24,%25,%26,%27,%28,%29,%30,%31," \
             "%32,%33,%34,%35,%36,%37,%38,%39,%40,%41,%42,%43,%44,%45,%46,%47,%48,%49,%50,%51,%52,%53,%54,%55,%56,%57,%58,%59,%60,%61,%62,%63," \
             "%64,%65,%66,%67,%68,%69,%70,%71,%72,%73,%74,%75,%76,%77,%78,%79,%80,%81,%82,%83,%84,%85,%86,%87,%88,%89,%90,%91,%92,%93,%94,%95," \
             "%96,%97,%98,%99,%100,%101,%102,%103,%104,%105,%106,%107,%108,%109,%110,%111,%112,%113,%114,%115,%116,%117,%118,%119,%120,%121,%122,%123,%124,%125,%126,%127}"
#define R128(d, e) R8(d, 0), R8(d, 8), R8(d, 16), R8(d, 24), R8(d, 32), R8(d, 40), R8(d, 48), R8(d, 56), \
                   R8(e, 0), R8(e, 8), R8(e, 16), R8(e, 24), R8(e, 32), R8(e, 40), R8(e, 48), R8(e, 56)
__device__ __forceinline__ void mma256_ss(float (&d)[64], float (&e)[64], uint64_t da, uint64_t db, int sc) {
  asm volatile("{\n.reg .pred p;\nsetp.ne.b32 p, %130, 0;\n"
               "wgmma.mma_async.sync.aligned.m64n256k16.f32.bf16.bf16 " D128 ", %128, %129, p, 1, 1, 0, 1;\n}"
               : R128(d, e) : "l"(da), "l"(db), "r"(sc));
}
__device__ __forceinline__ void mma256_rs(float (&d)[64], float (&e)[64], uint32_t a0, uint32_t a1, uint32_t a2, uint32_t a3, uint64_t db) {
  asm volatile("{\n.reg .pred p;\nsetp.ne.b32 p, 1, 0;\n"
               "wgmma.mma_async.sync.aligned.m64n256k16.f32.bf16.bf16 " D128 ", {%128,%129,%130,%131}, %132, p, 1, 1, 1;\n}"
               : R128(d, e) : "r"(a0), "r"(a1), "r"(a2), "r"(a3), "l"(db));
}
template <int N> __device__ __forceinline__ void keep(float (&a)[N]) {
#pragma unroll
  for (int i = 0; i < N; i++) asm volatile("" : "+f"(a[i])::"memory");
}
template <int N> __device__ __forceinline__ void keep(uint32_t (&a)[N]) {
#pragma unroll
  for (int i = 0; i < N; i++) asm volatile("" : "+r"(a[i])::"memory");
}

#define STAMP(idx) do {} while (0)
#define PROF(grp, cond, idx) do {} while (0)

constexpr float SCL2 = 1.4426950408889634f * 0.08838834764831845f;

__device__ __forceinline__ void pack_p(const float (&s)[64], uint32_t (&p)[32]) {
#pragma unroll
  for (int i = 0; i < 32; i++) p[i] = pack_bf(s[2 * i], s[2 * i + 1]);
}

__device__ __forceinline__ void issue_qk(float (&s)[64], uint32_t q0, uint32_t q1, uint32_t kslot) {
  const uint64_t db = make_desc(kslot, 16, 1024), da0 = make_desc(q0, 16, 1024), da1 = make_desc(q1, 16, 1024);
#pragma unroll
  for (int kk = 0; kk < 8; kk++) mma_ss<0>(s, (kk < 4 ? da0 : da1) + (kk & 3) * 2, db + (kk >> 2) * 1024 + (kk & 3) * 2, kk != 0);
}
__device__ __forceinline__ void issue_pv(float (&o)[64], uint32_t (&p)[32], uint32_t vslot, int acc) {
  uint64_t db = make_desc(vslot, 16384, 1024);
#pragma unroll
  for (int kk = 0; kk < 8; kk++)
    mma_rs<1>(o, p[4 * kk], p[4 * kk + 1], p[4 * kk + 2], p[4 * kk + 3], db + kk * 128, kk == 0 ? acc : 1);
}

template <int H>
__device__ __forceinline__ void store_chunk(const float (&a)[64], uint32_t addr) {
#pragma unroll
  for (int i = 8 * H; i < 8 * H + 8; i += 2)
    stmatrix4(addr ^ ((i & 7) << 4), pack_bf(a[4 * i], a[4 * i + 1]), pack_bf(a[4 * i + 2], a[4 * i + 3]),
              pack_bf(a[4 * i + 4], a[4 * i + 5]), pack_bf(a[4 * i + 6], a[4 * i + 7]));
}
template <int H>
__device__ __forceinline__ void store_chunk(const float (&a)[64], float i0, float i1, uint32_t addr) {
#pragma unroll
  for (int i = 8 * H; i < 8 * H + 8; i += 2)
    stmatrix4(addr ^ ((i & 7) << 4), pack_bf(a[4 * i] * i0, a[4 * i + 1] * i0), pack_bf(a[4 * i + 2] * i1, a[4 * i + 3] * i1),
              pack_bf(a[4 * i + 4] * i0, a[4 * i + 5] * i0), pack_bf(a[4 * i + 6] * i1, a[4 * i + 7] * i1));
}
__device__ __forceinline__ float inv_quad_sum(float l) {
  l += __shfl_xor_sync(0xffffffffu, l, 1);
  l += __shfl_xor_sync(0xffffffffu, l, 2);
  return rcp(l);
}

__device__ __forceinline__ void write_table(uint32_t table, bool ca, uint32_t t, const uint4& m0, const uint4& m1) {
  float c0 = untag_sum(m0.x, m1.x), c1 = untag_sum(m0.y, m1.y), c2 = untag_sum(m0.z, m1.z), c3 = untag_sum(m0.w, m1.w);
  if (ca) { c0 = 1.f + rbf(c0); c1 = 1.f + rbf(c1); c2 = 1.f + rbf(c2); c3 = 1.f + rbf(c3); }
  const uint32_t d = table + (t >> 2) * 64 + (t & 1) * 32 + (t & 2) * 2 + (ca ? 0 : 8);
  sts1(d, pack_bf(c0, c1));
  sts1(d + 16, pack_bf(c2, c3));
}

__device__ __forceinline__ void ln_scalars(float mean, float var, float& mb, float& sd) {
  mb = rbf(mean);
  float r; asm("sqrt.approx.ftz.f32 %0, %1;" : "=f"(r) : "f"(rbf(rbf(var) + 1e-5f)));
  sd = rbf(r);
}

__global__ void __cluster_dims__(2, 1, 1) __launch_bounds__(384, 1) fused_kernel(const __grid_constant__ Maps maps, const Ptrs P) {
  extern __shared__ __align__(1024) uint8_t smem_raw[];
  const uint32_t base = smem_u32(smem_raw);
  const int tid = threadIdx.x, lane = tid & 31;
  const int warp = __shfl_sync(0xffffffffu, tid >> 5, 0);
  const int b = blockIdx.x;
  PROF(31, tid == 0, 0);

  if (b >= NMAIN) {
    float* sc = reinterpret_cast<float*>(smem_raw);
    float* red = sc + DM;
    for (int k = tid; k < DM; k += 384) sc[k] = rbf(silu_f(__bfloat162float(P.c[k])));
    __syncthreads();
    if (tid < 256) {
      const int col = 2048 + (b - NMAIN) * 1024 + (tid & 127) * 8, r0 = (tid >> 7) * 512;
      float acc[8];
#pragma unroll
      for (int e = 0; e < 8; e++) acc[e] = 0.f;
#pragma unroll 1
      for (int r = r0; r < r0 + 512; r += HU) {
        uint4 w[HU];
#pragma unroll
        for (int u = 0; u < HU; u++) w[u] = ldg_stream4(P.w_mod + (size_t)(r + u) * NMOD + col);
#pragma unroll
        for (int u = 0; u < HU; u++) {
          float s = sc[r + u];
          acc[0] += s * bf_lo(w[u].x); acc[1] += s * bf_hi(w[u].x); acc[2] += s * bf_lo(w[u].y); acc[3] += s * bf_hi(w[u].y);
          acc[4] += s * bf_lo(w[u].z); acc[5] += s * bf_hi(w[u].z); acc[6] += s * bf_lo(w[u].w); acc[7] += s * bf_hi(w[u].w);
        }
      }
      if (tid >= 128) {
#pragma unroll
        for (int e = 0; e < 8; e++) red[(tid & 127) * 8 + e] = acc[e];
      }
      const uint32_t tag = ld_relaxed(&g_epoch) % 3 + 1;
      bar_sync(1, 256);
      if (tid < 128) {
        uint32_t o[8];
#pragma unroll
        for (int e = 0; e < 8; e++) o[e] = __float_as_uint(rbf(acc[e] + red[tid * 8 + e])) | tag;
        st_relaxed4(g_mod + col, o[0], o[1], o[2], o[3]);
        st_relaxed4(g_mod + col + 4, o[4], o[5], o[6], o[7]);
        const uint4 wr = ldg_nc4(P.w_r + tid * 8);
        const uint32_t wv[4] = {wr.x, wr.y, wr.z, wr.w};
        float dsum = 0.f;
#pragma unroll
        for (int e = 0; e < 8; e++) {
          const float m = bf_hi(o[e]);
          dsum += (b == NMAIN + 2 ? rbf(1.f + m) : m) * ((e & 1) ? bf_hi(wv[e >> 1]) : bf_lo(wv[e >> 1]));
        }
#pragma unroll
        for (int k = 16; k > 0; k >>= 1) dsum += __shfl_xor_sync(0xffffffffu, dsum, k);
        if (lane == 0) st_relaxed(g_mod + (b - NMAIN) * 4 + warp, tagf(dsum, tag));
      }
    }
    PROF(2, tid == 0, 1);
    return;
  }

  const int rank = b & 1;
  const int rb = ((b >> 4) << 1) | rank, cj = (b >> 1) & 7;
  const bool late = b & 4;
  const uint32_t bfull = base + OFF_BAR, bempty = bfull + NSLOT * 8;
  const uint32_t gfull = bempty + NSLOT * 8, gempty = gfull + 32;
  const uint32_t bar_ofull = gempty + 32;
  const uint32_t bar_ofree = bar_ofull + 32;
  const uint32_t bar_par = bar_ofree + 32;
  const uint32_t bar_mod = bar_par + 8;
  const uint32_t bar_pread = bar_mod + 8;
  const uint32_t bar_xres = bar_pread + 8;
  const uint32_t bar_ring = bar_xres + 8;
  const uint32_t bar_box = bar_ring + 24;
  const uint32_t bar_go = bar_box + 96;
  const uint32_t bar_go2 = bar_go + 16;
  const uint32_t bar_cnt = bar_go + 24;
  const uint32_t xfull = bar_go + 40, xempty = xfull + 32;
  const uint32_t bar_hw = xempty + 32, bar_hx = bar_hw + 8;
  const uint32_t bar_hpub = bar_hx + 16;
  const uint32_t bar_win = bar_hpub + 16;
  const uint32_t bar_rx = bar_win + 8;
  const uint32_t bar_sel = bar_rx + 8;
  const uint32_t bar_gate = bar_sel + 8;
  const uint32_t bar_rel = bar_gate + 8;
  const uint32_t bar_od = bar_rel + 8;
  const uint32_t bar_mod2 = bar_od + 8;
  const uint32_t bar_res = bar_go + 8;
  const uint32_t stage = base + OFF_STAGE, par = base + OFF_PAR;

  if (warp == 10 && elect_one()) prefetch_map(&maps.wm);
  if (warp == 8 && elect_one()) {
    for (int s = 0; s < NSLOT; s++) { mbar_init(bfull + s * 8, 1); mbar_init(bempty + s * 8, 16); }
    for (int s = 0; s < 4; s++) { mbar_init(gfull + s * 8, 1); mbar_init(gempty + s * 8, 16); mbar_init(xfull + s * 8, 1); mbar_init(xempty + s * 8, 8); mbar_init(bar_ofree + s * 8, 1); mbar_init(bar_ofull + s * 8, 128); }
    mbar_init(bar_par, 64); mbar_init(bar_mod, 256); mbar_init(bar_pread, 2); mbar_init(bar_xres, 1);
    mbar_init(bar_ring, 8); mbar_init(bar_ring + 8, 8); mbar_init(bar_ring + 16, 8);
    mbar_init(bar_go, 1); mbar_init(bar_go2, 1); mbar_init(bar_cnt, 1); mbar_init(bar_cnt + 8, 1); mbar_init(bar_hpub, 8); mbar_init(bar_hpub + 8, 8); mbar_init(bar_res, 1); mbar_init(bar_win, 1); mbar_init(bar_rx, 1); mbar_init(bar_sel, 64); mbar_init(bar_gate, 8); mbar_init(bar_rel, 8); mbar_init(bar_od, 1); mbar_init(bar_mod2, 64);
    for (int s = 0; s < 12; s++) mbar_init(bar_box + s * 8, 1);
    asm volatile("fence.mbarrier_init.release.cluster;" ::: "memory");
    prefetch_map(&maps.x); prefetch_map(&maps.wq); prefetch_map(&maps.k); prefetch_map(&maps.v);
  }
  if (warp == 9 && elect_one()) {
    mbar_init(bar_hw, 1); mbar_init(bar_hx, 1); mbar_init(bar_hx + 8, 1);
    asm volatile("fence.mbarrier_init.release.cluster;" ::: "memory");
    mbar_expect_tx(bar_hw, 32768);
    mbar_expect_tx(bar_hx, 16384);
    mbar_expect_tx(bar_hx + 8, 16384);
    const __nv_bfloat16* xs = P.x + (size_t)(rb * 128 + cj * 16) * DM;
    bulk_load(base + 2 * GST_BYTES, xs, 16384, bar_hx);
    if (!late) {
      tma2d(stage, &maps.wm, (b >> 1) * 32, rank * 512, bar_hw);
      tma2d(stage + 16384, &maps.wm, (b >> 1) * 32, rank * 512 + 256, bar_hw);
    }
    bulk_load(base + 3 * GST_BYTES, xs + 8 * DM, 16384, bar_hx + 8);
  }
  cluster_arrive();

  if (warp >= 8) {
    asm volatile("setmaxnreg.dec.sync.aligned.u32 40;");
    if (warp < 10) bar_arrive(1, 320);
    const uint32_t epoch = ld_relaxed(&g_epoch);
    cluster_wait();
    if (warp == 8) {
      const int kvrow = (cj >> 1) * SK + (SK - WIN);
      int wch = cj * 8 + rank * 2;
#pragma unroll 1
      for (int ps = 0; ps < 3; ps++) {
        const CUtensorMap* mw = ps == 2 ? &maps.wo : &maps.wq;
        const uint32_t xt = ps == 1 ? XT1 : XT2, wt = ps == 0 ? WT0 : (ps == 1 ? WT1 : WT2);
        const int nst = ps == 2 ? 32 : 16;
#pragma unroll 1
        for (int i = 0; i < nst; i++) {
          const uint32_t bf = gfull + (i & 3) * 8;
          const int kt = ps == 2 ? otile_of(i, cj) : (ps ? i : slice_of(i) + (b & 14)) & 15;
          const uint32_t wd = base + unit_of(wt, i & 3) + rank * UNIT, xd = base + unit_of(xt, i & 3);
          const uint8_t* xs = g_act + (uint32_t)(rb * 80 + (ps - 1) * 16 + kt) * UNIT;
          if (ps == 0 && i == HD) mbar_wait(bar_mod, 0);
          const bool xfirst = ps && i < 2;
          const bool own = ps == 2 && i >= 2 && i < 6;
          if (ps == 2 && i == 0) mbar_wait(bar_ofree + 24, 0);
          if (i == 0) fence_async();
          mbar_wait(gempty + (i & 3) * 8, ((i >> 2) & 1) ^ 1);
          if (elect_one()) {
            mbar_expect_tx(bf, ps && !own ? GST_BYTES : 2 * UNIT);
            if (xfirst) bulk_load_stream(xd, xs, UNIT, bf);
          }
          if (ps && i < 4) mbar_wait(bempty + i * 8, 1);
          if (elect_one()) tma3d_mc<true>(wd, mw, 0, (i == 31 ? kt ^ (rank * 8) : kt) * 64, i == 31 ? cj * 2 : wch, bf);
          if (ps) {
            if (i == 20 || i == 26) { mbar_wait(bar_cnt + (i & 2) * 4, 0); fence_async(); }
            if (i == RES0) mbar_wait(bar_res, 0);
            if (i == 4 * ps - 2) mbar_wait(bar_ofree + (ps - 1) * 16, 0);
            if (elect_one()) {
              if (i == 31) bulk_load(xd, xs, UNIT, bf); else if (!xfirst && !own) bulk_load_stream(xd, xs, UNIT, bf);
              mbar_arrive_pred(bar_go, i == GOST - 1);
              if (PG0 < 16) mbar_arrive_pred(bar_go2, ps == 1 && i == PG0);
              mbar_arrive_pred(bar_od, i == (ps == 1 ? ODS1 : ODS));
              if (i == RES0) mbar_expect_tx(bar_xres, 32768);
              if (i == RES0 || i == RES1) tma2d(base + OFF_RES + (i == RES1) * UNIT, &maps.x, cj * 128 + (i == RES1) * 64, rb * 128, bar_xres);
            }
          }
        }
        if (ps == 2) break;
        wch = ps ? ((wch >> 3) ^ rank) * 2 : wch + 4;
#pragma unroll 1
        for (int u = 0; u < 16; u++) {
          const bool isk = (u == 0) || ((u & 1) && u < 15);
          const int blk = (isk ? (u + 1) >> 1 : (u == 15 ? 7 : (u >> 1) - 1)) & 3;
          const uint32_t sl = base + unit_of(ps ? AT1 : AT0, u & 3) + rank * UNIT, bf = bfull + (u & 3) * 8;
          if (u < 4) mbar_wait(gempty + ((u + 1) >> 1) * 8, 1);
          mbar_wait(bempty + (u & 3) * 8, ((u >> 2) & 1) ^ 1);
          if (elect_one()) {
            mbar_arrive_pred(bar_go2, ps && u + 16 == PG0);
            mbar_expect_tx(bf, SLOT_BYTES);
            tma3d_mc<false>(sl, isk ? &maps.k : &maps.v, 0, kvrow + blk * 128, rank, bf);
          }
        }
      }
      if (elect_one()) mbar_expect_tx(bar_rx, UNIT);
      mbar_wait(bar_rel, 0);
      if (elect_one()) {
        bulk_load_stream(base + UNIT, g_act + (uint32_t)(rb * 80 + 16 + (cj ^ 7) * 8 + 7) * UNIT, UNIT, bar_rx);
      }
      if (b < NFFN) {
#pragma unroll 1
        for (int u = 0; u < 12; u++) {
          const uint32_t dst = base + unit_of(u < 4 ? FT_G : (u < 8 ? FT_U : FT_D), u & 3);
          if (elect_one()) mbar_expect_tx(bar_box + u * 8, UNIT);
          if (u == FB0 || u == FB1 || u == FB2) mbar_wait(bar_ring + (u == FB2 ? 16 : u == FB1 ? 8 : 0), 0);
          const int fp = u < FPB ? FPACE0 : FPACE;
          if (u >= fp) mbar_wait(bar_box + (u - fp) * 8, 0);
          if (elect_one()) {
            if (u < 8) tma2d(dst, u < 4 ? &maps.wg : &maps.wu, b * 32, (u & 3) * 256, bar_box + u * 8);
            else tma3d(dst, &maps.wd, 0, b * 32, (u - 8) * 4, bar_box + u * 8);
          }
        }
      }
    } else if (warp == 9) {
      const uint32_t target = 8 * (epoch + 1);
      uint32_t hmask = 0;
#pragma unroll 1
      for (int i = 0; i < 16; i++) {
        if (i == HDX) mbar_wait(bar_mod, 0);
        const int kt = (2 * cj + slice_of(i)) & 15;
        const uint32_t need = i == 15 ? 0xffffu : 1u << kt;
        if (i >= NRS && (hmask & need) != need) {
          uint32_t n = 0;
          do { hmask = __ballot_sync(0xffffffffu, ld_acquire(&g_cnt_h[rb * 32 + (lane & 15)]) == epoch + 1); watchdog(n); } while ((hmask & need) != need);
          PROF(1, lane == 0 && i == NRS, 26);
          fence_async();
        }
        mbar_wait(xempty + (i & 3) * 8, ((i >> 2) & 1) ^ 1);
        if (elect_one()) {
          mbar_expect_tx(xfull + (i & 3) * 8, UNIT);
          if (i < NRS) tma2d(base + (i & 3) * GST_BYTES, &maps.x, kt * 64, rb * 128, xfull + (i & 3) * 8);
          else bulk_load_stream(base + (i & 3) * GST_BYTES, g_act + (uint32_t)(rb * 80 + kt) * UNIT, UNIT, xfull + (i & 3) * 8);
        }
      }
      prefetch_map(&maps.wo);
#pragma unroll 1
      for (int t = 0; t < 4; t++) {
        if (t & 1) mbar_wait(bar_od, t >> 1);
#pragma unroll 1
        for (int p = 0; p < 32768 / OPS; p++) {
          const uint32_t w = p / (16384 / OPS), c = (p / (8192 / OPS)) & 1, off = w * 8192 + (p % (8192 / OPS)) * OPS;
          mbar_wait(bar_ofull + (t & 1) * 16 + w * 8, t >> 1);
          if (elect_one()) {
            bulk_store(g_act + (uint32_t)(rb * 80 + 16 + (cj * 4 + t) * 2 + c) * UNIT + off, base + unit_of(QT, 2 * t + c) + off, OPS);
            asm volatile("cp.async.bulk.commit_group;" ::: "memory");
            asm volatile("cp.async.bulk.wait_group.read %0;" ::"n"(OFL) : "memory");
          }
        }
        if (elect_one()) {
          asm volatile("cp.async.bulk.wait_group.read 0;" ::: "memory");
          mbar_arrive(t < 3 ? bar_ofree + t * 8 : bar_res);
          asm volatile("cp.async.bulk.wait_group 0;" ::: "memory");
          fence_async();
          red_release(&g_cnt_o[((rb * 4 + t) * 2 + (cj & 1)) * 32], 2);
        }
        if (t) {
          wait_counter(&g_cnt_o[(rb * 8 + 2 * t + (cj & 1)) * 32], target);
          if (t & 1) wait_counter(&g_cnt_o[(rb * 8 + (t == 1 ? cj & 1 : 7 - (cj & 1))) * 32], target);
          if (elect_one()) mbar_arrive(t == 1 ? bar_ofree + 24 : bar_cnt + t * 8 - 16);
        }
      }
      PROF(2, lane == 0, 27);
      const uint32_t tag = epoch % 3 + 1;
      const uint32_t* inbox = g_cand + (b >> 1) % CR * 512 + (lane & 15) * CS;
      mbar_wait(bar_ring + 16, 0);
      uint32_t c0 = ld_relaxed(inbox), n = 0;
#define CAND_STEP(cv)                                                                                        \
      {                                                                                                      \
        const bool valid = (cv & 3u) == tag, all = __all_sync(0xffffffffu, valid);                           \
        const uint32_t best = __reduce_max_sync(0xffffffffu, valid ? cv : 0u);                               \
        const uint32_t blk = __ffs(__ballot_sync(0xffffffffu, cv == best)) - 1;                              \
        if (best) sts2(par + PAR_CONST + 56, best, (blk << 7 | (~best >> 2 & 127)) | (all ? 0x1800 : 0x800)); \
        if (all) break;                                                                                      \
        cv = ld_relaxed(inbox);                                                                              \
      }
      while (true) { CAND_STEP(c0) watchdog(n); }
    } else {
      const int t2 = tid - 320;
      if (late && warp == 10) {
        mbar_wait(bar_hx, 0);
        if (elect_one()) {
          tma2d(stage, &maps.wm, (b >> 1) * 32, rank * 512, bar_hw);
          tma2d(stage + 16384, &maps.wm, (b >> 1) * 32, rank * 512 + 256, bar_hw);
        }
      }
      {
        const uint32_t tag = epoch % 3 + 1;
        mbar_wait(bar_hx + 8, 0);
        mbar_wait(bar_hw, 0);
        __nanosleep(late ? OSL2 : OSL);
        {
          const uint32_t t7 = (warp & 1) * 64 + (lane >> 4) * 32 + 16 + (lane & 15);
          const uint32_t* pm = g_modp + ((cj * 128 + t7 * 4) & (DM - 1));
          uint4 m0, m1, m2, m3;
          uint32_t n = 0;
          do {
            m0 = ld_relaxed4(pm); m1 = ld_relaxed4(pm + 2 * DM); m2 = ld_relaxed4(pm + DM); m3 = ld_relaxed4(pm + 3 * DM);
            watchdog(n);
          } while (!__all_sync(0xffffffffu, tag_ok(m0, tag) && tag_ok(m1, tag) && tag_ok(m2, tag) && tag_ok(m3, tag)));
          write_table(par, false, t7, m0, m1);
          write_table(par, true, t7, m2, m3);
          mbar_arrive(bar_mod2);
        }
      }
      mbar_wait(bar_hpub + (warp & 1) * 8, 0);
      PROF(1, t2 == 0, 24);
#pragma unroll 1
      for (int c = 0; c < 8; c++) {
        const uint32_t off = (warp & 1) * UNIT + c * 2048 + lane * 16;
        uint8_t* dst = g_act + (uint32_t)(rb * 80 + cj * 2) * UNIT + off;
        const uint4 v0 = lds4(stage + off), v1 = lds4(stage + off + 512), v2 = lds4(stage + off + 1024), v3 = lds4(stage + off + 1536);
        stg4(dst, v0); stg4(dst + 512, v1); stg4(dst + 1024, v2); stg4(dst + 1536, v3);
      }
      __syncwarp();
      PROF(1, t2 == 0, 15);
      if (lane == 0) {
        mbar_arrive(bar_pread);
        red_release(&g_cnt_h[rb * 32 + cj * 2 + (warp & 1)], 1);
        PROF(1, t2 == 0, 25);
        prefetch_map(&maps.wg); prefetch_map(&maps.wu); prefetch_map(&maps.wd); prefetch_map(&maps.out);
      }
      __syncwarp();
      if (b < NFFN) {
        mbar_wait(bar_go2, 0);
        const __nv_bfloat16* pg = ((b & 1) ? P.w_up : P.w_gate) + (b >> 1) * 64 + (size_t)t2 * FF;
        const __nv_bfloat16* pd = P.w_down + (size_t)b * 32768 + t2 * 64;
        PROF(2, t2 == 0, 13);
#pragma unroll 1
        for (int i = 0; i < WN; i += WB) {
          uint32_t v[WB];
#pragma unroll
          for (int u = 0; u < WB; u++) {
            const int k = i + u;
            asm volatile("ld.global.cg.L2::128B.u32 %0, [%1];" : "=r"(v[u]) : "l"(k < 16 ? pg + (size_t)k * 64 * FF : pd + (k - 16) * 4096));
          }
#pragma unroll
          for (int u = 1; u < WB; u++) v[0] ^= v[u];
          sts1(par + PAR_SINK + t2 * 4, v[0]);
        }
        PROF(2, t2 == 0, 14);
      }
      const uint32_t tag = epoch % 3 + 1;
      mbar_wait(bar_go, 0);
      bar_sync(4, 64);
      if (warp == 10) {
        const uint32_t* src = g_mod + 2 * DM + cj * 128 + lane * 4;
        const uint2 wr = *reinterpret_cast<const uint2*>(P.w_r + cj * 128 + lane * 4);
        uint4 vga, vsb, vcb, vgb;
        uint32_t n = 0;
        do {
          vga = ld_relaxed4(src); vsb = ld_relaxed4(src + DM); vcb = ld_relaxed4(src + 2 * DM); vgb = ld_relaxed4(src + 3 * DM);
          watchdog(n);
        } while (!__all_sync(0xffffffffu, tag_ok(vga, tag) && tag_ok(vsb, tag) && tag_ok(vcb, tag) && tag_ok(vgb, tag)));
        const float c0 = rbf(1.f + bf_hi(vcb.x)), c1 = rbf(1.f + bf_hi(vcb.y)), c2 = rbf(1.f + bf_hi(vcb.z)), c3 = rbf(1.f + bf_hi(vcb.w));
        const float a0 = c0 * bf_lo(wr.x), a1 = c1 * bf_hi(wr.x), a2 = c2 * bf_lo(wr.y), a3 = c3 * bf_hi(wr.y);
        const uint32_t h0 = pack_bf(a0, a1), h1 = pack_bf(a2, a3);
        const uint32_t t1 = par + PAR_T1 + (lane >> 2) * 64 + (lane & 1) * 32 + (lane & 2) * 2;
        sts1(t1, h0); sts1(t1 + 8, pack_bf(a0 - bf_lo(h0), a1 - bf_hi(h0)));
        sts1(t1 + 16, h1); sts1(t1 + 24, pack_bf(a2 - bf_lo(h1), a3 - bf_hi(h1)));
        const uint32_t tg = par + PAR_SINK + (lane >> 3) * 64 + (lane & 1) * 32 + (lane & 6) * 2;
        sts1(tg, __byte_perm(vga.x, vga.y, 0x7632)); sts1(tg + 16, __byte_perm(vga.z, vga.w, 0x7632));
        sts4(par + PAR_T2 + lane * 32, make_uint4(pack_bf(c0, c1), __byte_perm(vsb.x, vsb.y, 0x7632), __byte_perm(vgb.x, vgb.y, 0x7632), __byte_perm(vga.x, vga.y, 0x7632)));
        sts4(par + PAR_T2 + lane * 32 + 16, make_uint4(pack_bf(c2, c3), __byte_perm(vsb.z, vsb.w, 0x7632), __byte_perm(vgb.z, vgb.w, 0x7632), __byte_perm(vga.z, vga.w, 0x7632)));
      } else {
        const uint4 g = poll4((lane & 8) ? g_mod + 8 - (lane & 1) * 4 : g_mod + 5 * DM + (b >> 4) * 128 + (lane & 7) * 16 + (b & 12), tag);
        sts1(par + PAR_CONST + 60, 0);
        if (lane < 8) sts1(par + PAR_CONST + 16 + lane * 4, (b & 2) ? ((b & 1) ? g.w : g.z) : ((b & 1) ? g.y : g.x));
        else if (lane < 10) sts2(par + PAR_CONST + (lane - 8) * 8, __float_as_uint(untag_sum(g.x, g.y) + untag_sum(g.z, g.w)), epoch);
      }
      __syncwarp();
#pragma unroll 4
      for (int q = 0; q < 32; q++) st_b128(g_xch + ((size_t)b * 8 * 256 + q * 64 + t2) * 4, (epoch & 1) << 16, 0, 0, 0);
      for (int q = 0; q < 2; q++) st_relaxed4(g_stats + ((size_t)cj * SEQ + rb * 128 + q * 64 + t2) * 4, 0, 0, 0, 0);
      if (b < NFFN)
        for (int q = 0; q < 2; q++) st_relaxed4(ypart_slot(b, q * 64 + t2), 0, 0, 0, 0);
      st_relaxed4(g_row + rb * 2 * DM + (t2 >> 5) * DM + cj * 128 + (t2 & 31) * 4, 0, 0, 0, 0);
      __threadfence();
      mbar_arrive(bar_par);
      mbar_wait(bar_gate, 0);
      uint32_t have = 0, n = 0;
      while (true) {
        const uint32_t st = lds1(par + PAR_CONST + 60) >> 7;
        if ((st & 31) != have) {
          const uint32_t* hsrc = g_row + (st & 15) * 2 * DM + t2 * 4;
          uint4 hv[4];
          bool ok = true;
#pragma unroll
          for (int i = 0; i < 4; i++) hv[i] = ld_pairs(hsrc + i * 256);
#pragma unroll
          for (int i = 0; i < 4; i++) {
            sts2(base + ((FT_G >> i * 4) & 15) * UNIT + (warp & 1) * 8192 + 256 + lane * 8, hv[i].x, hv[i].z);
            ok = ok && hv[i].y == tag && hv[i].w == tag;
          }
          have = __all_sync(0xffffffffu, ok) ? st & 31 : 0;
        }
        if ((st ^ have) == 32) break;
        watchdog(n);
      }
      mbar_arrive(bar_sel);
    }
    __syncwarp();
    cluster_arrive();
    {
      const uint32_t tag = epoch % 3 + 1, t3 = tid - 256;
      mbar_wait(bar_win, 0);
      uint2 win = lds2(par + PAR_CONST + 56);
      win.y &= 0x7ff;
      const uint32_t* fsrc = g_row + (win.y >> 7) * 2 * DM + (b >> 4) * 128 + (t3 & 7) * 16 + (b & 6) * 2 + ((b >> 2) & 2);
      const uint32_t* ysrc = ypart_slot(min(t3, NFFN - 1), b);
      uint2 fh = ld_pair(fsrc), fx = ld_pair(fsrc + DM);
      uint4 ya = ld_b128(ysrc);
      const float rwin = __uint_as_float(((int)win.x < 0 ? win.x & 0x7fffffffu : ~win.x) & ~0x1ffu);
      const float rs = rbf(rcp(1.f + __expf(-rbf(rwin))));
      uint32_t n = 0;
      while (__any_sync(0xffffffffu, fh.y != tag || fx.y != tag)) { fh = ld_pair(fsrc); fx = ld_pair(fsrc + DM); watchdog(n); }
      while (true) {
        const bool miss = ((ya.x & 1) | (ya.y & 1) << 1) != tag;
        if (!__any_sync(0xffffffffu, miss)) break;
        if (miss) ya = ld_b128(ysrc);
        watchdog(n);
      }
      PROF(8, t3 == 0, 5);
      float y[8] = {bf_lo(ya.x & ~1u), bf_hi(ya.x), bf_lo(ya.y & ~1u), bf_hi(ya.y), bf_lo(ya.z), bf_hi(ya.z), bf_lo(ya.w), bf_hi(ya.w)};
#pragma unroll
      for (int h = 4; h > 0; h >>= 1) {
        const bool up = lane & (h * 2);
#pragma unroll
        for (int e = 0; e < h; e++) y[e] = (up ? y[e + h] : y[e]) + __shfl_xor_sync(0xffffffffu, up ? y[e] : y[e + h], h * 2);
      }
      y[0] += __shfl_xor_sync(0xffffffffu, y[0], 1);
      if (!(lane & 1)) sts1(par + PAR_RED + 64 + t3 * 2, __float_as_uint(y[0]));
      bar_sync(4, 128);
      if (t3 < 8) {
        float y0 = 0.f;
#pragma unroll
        for (int w7 = 0; w7 < 7; w7++) y0 += __uint_as_float(lds1(par + PAR_RED + 64 + w7 * 32 + t3 * 4));
        const uint32_t gv = lds1(par + PAR_CONST + 16 + t3 * 4);
        const uint32_t upd = hmul2(pack_bf(y0, y0), pack_bf(rs, rs));
        const uint32_t r = hadd2(fx.x, hmul2(__byte_perm(gv, gv, 0x3232), hadd2(fh.x, upd)));
        reinterpret_cast<uint16_t*>(P.out)[(size_t)win.y * DM + (b >> 4) * 128 + t3 * 16 + (b & 15)] = (b & 1) ? r >> 16 : r;
        if (b == 0 && t3 == 0) st_relaxed(&g_epoch, epoch + 1);
      }
      PROF(31, t3 == 0, 36);
    }
    cluster_wait();
  } else {
    const int wg = warp >> 2;

    uint32_t tag;
    {
      uint32_t* const pmod = g_modp + rank * 2 * DM + (b >> 1) * 32 + lane;
      uint32_t* const pln = g_ln1 + (rb * 128 + cj * 16 + warp) * 4;
      uint32_t sc[8];
#pragma unroll
      for (int k = 0; k < 8; k++) sc[k] = ldg_nc1(P.c + rank * 512 + warp * 64 + k * 8 + (lane & 3) * 2);
      const uint32_t epoch = ld_relaxed(&g_epoch);
      if (warp == 0) st_relaxed(pmod, 0);
      if (lane == 0) { st_b128(pln, 0, 0, 0, 0); st_b128(pln + 32, 0, 0, 0, 0); }
      asm volatile("setmaxnreg.inc.sync.aligned.u32 232;");
      bar_sync(1, 320);
#pragma unroll
      for (int k = 0; k < 8; k++) sc[k] = pack_bf(silu_f(bf_lo(sc[k])), silu_f(bf_hi(sc[k])));
      keep(sc);
      tag = epoch % 3 + 1;
#pragma unroll
      for (int part = 0; part < 4; part++) {
        if (!(part & 1)) {
          const uint32_t xa = base + (2 + part / 2) * GST_BYTES + warp * 2048 + lane * 16;
          mbar_wait(bar_hx + part * 4, 0);
          float s0 = 0.f, s1 = 0.f, q0 = 0.f, q1 = 0.f;
#pragma unroll
          for (int q = 0; q < 4; q++) {
            const uint4 xv = lds4(xa + q * 512);
            const uint32_t u[4] = {xv.x, xv.y, xv.z, xv.w};
#pragma unroll
            for (int e = 0; e < 4; e++) { const float lo = bf_lo(u[e]), hi = bf_hi(u[e]); s0 += lo; s1 += hi; q0 += lo * lo; q1 += hi * hi; }
          }
          s0 += s1; q0 += q1;
#pragma unroll
          for (int o = 16; o > 0; o >>= 1) { s0 += __shfl_xor_sync(0xffffffffu, s0, o); q0 += __shfl_xor_sync(0xffffffffu, q0, o); }
          const float mean = s0 * (1.f / DM);
          float mb, sd;
          ln_scalars(mean, fmaxf(q0 * (1.f / DM) - mean * mean, 0.f), mb, sd);
          uint32_t ih, il;
          split_inv(sd, ih, il);
          if (lane == 0) st_b128(pln + part * 16, pack_bf(mb, mb), ih, il, tag);
          PROF(1, tid == 0 && part == 2, 4);
        } else if (late == (part == 3)) {
          const uint32_t fr = (lane & 7) + (lane >> 4) * 8, tq = lane & 3;
          const uint32_t wa = stage + warp * 4096 + fr * 64 + ((((lane >> 3) & 1) ^ ((fr >> 1) & 3)) << 4);
          float d0[4] = {0.f, 0.f, 0.f, 0.f}, d1[4] = {0.f, 0.f, 0.f, 0.f};
          mbar_wait(bar_hw, 0);
#pragma unroll
          for (int ks = 0; ks < 4; ks++) {
            uint32_t w[8];
            ldmatrix4t(wa + ks * 1024, w[0], w[1], w[2], w[3]);
            ldmatrix4t((wa ^ 32) + ks * 1024, w[4], w[5], w[6], w[7]);
            mma16816(d0, w[0], w[1], w[2], w[3], sc[2 * ks], sc[2 * ks + 1]);
            mma16816(d1, w[4], w[5], w[6], w[7], sc[2 * ks], sc[2 * ks + 1]);
          }
          sts1(base + 2 * GST_BYTES + warp * 2048 + (tq * 8 + (lane >> 2)) * 4, __float_as_uint((tq & 2) ? ((tq & 1) ? d1[2] : d1[0]) : ((tq & 1) ? d0[2] : d0[0])));
          bar_sync(1, 256);
          if (warp == 0) {
            float s = 0.f;
#pragma unroll
            for (int w8 = 0; w8 < 8; w8++) s += __uint_as_float(lds1(base + 2 * GST_BYTES + w8 * 2048 + lane * 4));
            st_relaxed(pmod, (__float_as_uint(s) & ~3u) | tag);
          }
          PROF(1, tid == 0, 3);
        }
      }
      cluster_wait();
      if (wg == 1) bar_arrive(2, 256);
    }

    float f0 = 0.f, f1 = 0.f;
    const uint32_t rempty = lane < 2 ? mapa(bempty, lane & 1) : 0;
    constexpr uint32_t GE = NSLOT * 8 + 32;
    float o[64], s[64];
#pragma unroll 1
    for (int ps = 0; ps < 3; ps++) {
      {
        const uint32_t xt = ps == 1 ? XT1 : XT2, wt = ps == 1 ? WT1 : WT2;
        const int nst = ps == 2 ? 28 : 14;
        if (ps == 0) {
          float ga[64], gb[64];
#pragma unroll
          for (int i = 0; i < 64; i++) { ga[i] = 0.f; gb[i] = 0.f; }
          uint32_t a[2][16];
          const uint32_t l = fresh_lane();
          uint32_t fa[4];
#pragma unroll
          for (int kk = 0; kk < 4; kk++) fa[kk] = (base + wg * 8192 + frag_offset(warp)) ^ (kk * 32);
          const uint32_t mt = par + (l & 3) * 16;
          auto fetch = [&](int i, uint32_t (&f)[16], uint32_t z) {
            mbar_wait(xfull + (i & 3) * 8, i >> 2);
#pragma unroll
            for (int kk = 0; kk < 4; kk++) ldmatrix4(fa[kk] + (i & 3) * GST_BYTES + z, f[4 * kk], f[4 * kk + 1], f[4 * kk + 2], f[4 * kk + 3]);
          };
          const bool oddw = warp & 2;
          uint4 r0, r1;
          {
            const uint32_t t7 = (warp & 1) * 64 + (l >> 4) * 32 + (l & 15);
            const uint32_t* pm = g_modp + wg * DM + ((cj * 128 + t7 * 4) & (DM - 1));
            const uint32_t* pr = g_ln1 + (rb * 128 + warp * 16 + (l >> 2)) * 4;
            uint4 m0 = make_uint4(tag, tag, tag, tag), m1 = m0;
            if (!oddw) { m0 = ld_relaxed4(pm); m1 = ld_relaxed4(pm + 2 * DM); }
            r0 = ld_b128(pr); r1 = ld_b128(pr + 32);
            fetch(0, a[0], 0); fetch(1, a[1], 0);
            uint32_t n = 0;
            bool written = false;
#pragma unroll 1
            while (true) {
              uint32_t miss;
              asm volatile("{ .reg .pred p0, p1, p2, p3; .reg .b32 t, u;\n"
                           "lop3.b32 t, %1, %2, %19, 0x7e; lop3.b32 u, %3, %4, %19, 0x7e; or.b32 t, t, u; and.b32 t, t, 3; setp.ne.u32 p0, t, 0;\n"
                           "lop3.b32 t, %5, %6, %19, 0x7e; lop3.b32 u, %7, %8, %19, 0x7e; or.b32 t, t, u; and.b32 t, t, 3; setp.ne.u32 p1, t, 0;\n"
                           "setp.ne.u32 p2, %12, %19; setp.ne.u32 p3, %16, %19;\n"
                           "@p0 ld.relaxed.gpu.global.v4.u32 {%1, %2, %3, %4}, [%17];\n"
                           "@p1 ld.relaxed.gpu.global.v4.u32 {%5, %6, %7, %8}, [%17 + 8192];\n"
                           "@p2 ld.relaxed.gpu.global.v4.u32 {%9, %10, %11, %12}, [%18];\n"
                           "@p3 ld.relaxed.gpu.global.v4.u32 {%13, %14, %15, %16}, [%18 + 128];\n"
                           "or.pred p0, p0, p1; or.pred p2, p2, p3; vote.sync.any.pred p0, p0, 0xffffffff; vote.sync.any.pred p2, p2, 0xffffffff;\n"
                           "selp.u32 t, 1, 0, p0; selp.u32 u, 2, 0, p2; or.b32 %0, t, u; }"
                           : "=r"(miss), "+r"(m0.x), "+r"(m0.y), "+r"(m0.z), "+r"(m0.w), "+r"(m1.x), "+r"(m1.y), "+r"(m1.z), "+r"(m1.w),
                             "+r"(r0.x), "+r"(r0.y), "+r"(r0.z), "+r"(r0.w), "+r"(r1.x), "+r"(r1.y), "+r"(r1.z), "+r"(r1.w)
                           : "l"(pm), "l"(pr), "r"(tag) : "memory");
              if (!(miss & 1) && !written) {
                written = true;
                if (!oddw) write_table(par, wg, t7, m0, m1);
                mbar_arrive(bar_mod);
              }
              if (!miss) break;
              watchdog(n);
            }
          }
          const uint32_t zero = r0.w ^ tag;
          auto normalize = [&](uint32_t (&f)[16]) {
#pragma unroll
            for (int k = 0; k < 16; k += 2) { f[k] = ln_norm(f[k], r0.x, r0.y, r0.z); f[k + 1] = ln_norm(f[k + 1], r1.x, r1.y, r1.z); }
          };
          auto modulate = [&](int i, uint32_t (&f)[16]) {
#pragma unroll
            for (int kk = 0; kk < 4; kk++) {
              const uint4 m = lds4(mt + slice_of(i) * 256 + kk * 64);
              f[4 * kk] = MODUL(f[4 * kk], m.x, m.z); f[4 * kk + 1] = MODUL(f[4 * kk + 1], m.x, m.z);
              f[4 * kk + 2] = MODUL(f[4 * kk + 2], m.y, m.w); f[4 * kk + 3] = MODUL(f[4 * kk + 3], m.y, m.w);
            }
            keep(f);
            mbar_arrive_pred(xempty + (i & 3) * 8, l == 0);
          };
          auto publish = [&](int u, uint32_t (&f)[16]) {
#pragma unroll
            for (int kk = 0; kk < 4; kk++) stmatrix4(fa[kk] + OFF_STAGE + u * UNIT, f[4 * kk], f[4 * kk + 1], f[4 * kk + 2], f[4 * kk + 3]);
            __syncwarp();
            mbar_arrive_pred(bar_hpub + u * 8, l == 0);
          };
          auto multiply = [&](int i, uint32_t (&f)[16]) {
            mbar_wait(gfull + (i & 3) * 8, i >> 2);
            const uint64_t db = make_desc(base + (i & 3) * GST_BYTES + UNIT, 8192, 1024);
            wg_fence();
#pragma unroll
            for (int kk = 0; kk < 4; kk++) mma256_rs(ga, gb, f[4 * kk], f[4 * kk + 1], f[4 * kk + 2], f[4 * kk + 3], db + kk * 128);
            wg_commit();
          };
          auto next = [&](int i, uint32_t (&f)[16]) {
            wg_wait<1>();
            mbar_arrive_cl(rempty, GE + ((i + 2) & 3) * 8);
            uint32_t z = zero;
#pragma unroll
            for (int k = 0; k < 16; k += 2) asm volatile("lop3.b32 %0, %1, %2, %0, 0xA8;" : "+r"(z) : "r"(f[k]), "r"(f[k + 1]));
            fetch(i, f, z);
            normalize(f);
            if (i == 2) { keep(f); mbar_wait(bar_mod2, 0); }
            modulate(i, f); multiply(i, f);
          };
          normalize(a[0]); normalize(a[1]);
          keep(a[0]); keep(a[1]);
          mbar_wait(bar_mod, 0);
          PROF(1, tid == 0, 2);
          modulate(0, a[0]); multiply(0, a[0]); publish(0, a[0]);
          modulate(1, a[1]); multiply(1, a[1]);
#pragma unroll 1
          for (int i = 2; i < NRS; i += 2) {
            next(i, a[0]);
            if (i == 2) publish(1, a[0]);
            next(i + 1, a[1]);
          }
          wg_wait<1>();
          mbar_arrive_cl(rempty, GE + ((NRS + 2) & 3) * 8);
#pragma unroll 1
          for (int i = NRS; i < 14; i++) {
            mbar_wait(xfull + (i & 3) * 8, (i >> 2) & 1);
            mbar_wait(gfull + (i & 3) * 8, (i >> 2) & 1);
            const uint32_t xa = base + (i & 3) * GST_BYTES;
            const uint64_t da = make_desc(xa + wg * 8192, 16, 1024), db = make_desc(xa + UNIT, 8192, 1024);
            if (i == 13) bar_sync(2 + wg, 256);
            wg_fence();
#pragma unroll
            for (int kk = 0; kk < 4; kk++) mma256_ss(ga, gb, da + kk * 2, db + kk * 128, 1);
            wg_commit();
            if (i == 13) bar_arrive(3 - wg, 256);
            wg_wait<1>();
            uint32_t z = zero;
#pragma unroll
            for (int k = 0; k < 16; k += 2) asm volatile("lop3.b32 %0, %1, %2, %0, 0xA8;" : "+r"(z) : "r"(a[1][k]), "r"(a[1][k + 1]));
            mbar_arrive_cl(rempty, GE + ((i + 3) & 3) * 8 + z);
            mbar_arrive_pred(xempty + ((i + 3) & 3) * 8, l == 0 && i != NRS);
          }
          mbar_wait(xfull + 16, 1);
          wg_wait<0>();
          keep(ga); keep(gb);
#pragma unroll
          for (int i = 0; i < 64; i++) {
            asm volatile("mov.b32 %0, %1;" : "=f"(s[i]) : "f"(ga[i]));
            asm volatile("mov.b32 %0, %1;" : "=f"(o[i]) : "f"(gb[i]));
          }
        } else {
          float ga[64], gb[64];
#pragma unroll
          for (int i = 0; i < 64; i++) {
            asm volatile("mov.b32 %0, %1;" : "=f"(ga[i]) : "f"(s[i]));
            asm volatile("mov.b32 %0, %1;" : "=f"(gb[i]) : "f"(o[i]));
          }
#pragma unroll 1
          for (int i = 0; i < nst; i++) {
            mbar_wait(gfull + (i & 3) * 8, (i >> 2) & 1);
            const uint64_t da = make_desc(base + unit_of(ps == 2 && (i >> 2) == 1 ? XT2B : xt, i & 3) + wg * 8192, 16, 1024), db = make_desc(base + unit_of(wt, i & 3), 8192, 1024);
            if (i == nst - 1) bar_sync(2 + wg, 256);
            wg_fence();
#pragma unroll
            for (int kk = 0; kk < 4; kk++) mma256_ss(ga, gb, da + kk * 2, db + kk * 128, kk ? 1 : i);
            wg_commit();
            if (i == nst - 1) bar_arrive(3 - wg, 256);
            wg_wait<1>();
            mbar_arrive_cl(rempty, GE + ((i + 3) & 3) * 8, i != 0);
            PROF(4, tid == 0 && (i & 3) == 0, 40 + (ps - 1) * 4 + i / 4);
          }
          wg_wait<0>();
          keep(ga); keep(gb);
#pragma unroll
          for (int i = 0; i < 64; i++) {
            asm volatile("mov.b32 %0, %1;" : "=f"(s[i]) : "f"(ga[i]));
            asm volatile("mov.b32 %0, %1;" : "=f"(o[i]) : "f"(gb[i]));
          }
        }
        mbar_arrive_cl(rempty, GE + (ps == 2 ? 24 : 8));
        if (ps == 2) break;
      }
      const uint32_t qw = base + wg * 8192, qt = QT >> (16 * ps), at = ps ? AT1 : AT0;
      {
        const uint32_t wt = ps ? WT1 : WT0;
        const uint64_t da0 = make_desc(qw + unit_of(qt, 2), 16, 1024), da1 = make_desc(qw + unit_of(qt, 3), 16, 1024);
        const uint64_t db0 = make_desc(base + unit_of(wt, 2), 8192, 1024), db1 = make_desc(base + unit_of(wt, 3), 8192, 1024);
        mbar_wait(gfull + 16, 1);
        bar_sync(2 + wg, 256);
        wg_fence();
#pragma unroll
        for (int kk = 0; kk < 4; kk++) mma_ss<1>(s, da0 + kk * 2, db0 + kk * 128, 1);
        wg_commit();
        mbar_wait(xfull + 24, 1);
        mbar_wait(gfull + 24, 1);
        wg_fence();
#pragma unroll
        for (int kk = 0; kk < 4; kk++) mma_ss<1>(s, da1 + kk * 2, db1 + kk * 128, 1);
        wg_commit();
        bar_arrive(3 - wg, 256);
        mbar_wait(ps == 0 ? bar_pread : bar_ofree + 8, 0);
        wg_wait<0>();
        keep(s);
        PROF(2, tid == 0, 8 + ps * 8);
        uint32_t q[32];
        pack_p(s, q);
#pragma unroll
        for (int i = 0; i < 4; i++) stmatrix4((qw + unit_of(qt, 0) + frag_offset(warp)) ^ (i << 5), q[4 * i], q[4 * i + 1], q[4 * i + 2], q[4 * i + 3]);
        keep(q);
        bar_sync(2 + wg, 256);
        wg_fence();
#pragma unroll
        for (int kk = 0; kk < 8; kk++) mma_ss<1>(o, (kk < 4 ? da0 : da1) + (kk & 3) * 2, (kk < 4 ? db0 : db1) + UNIT / 16 + (kk & 3) * 128, 1);
        wg_commit();
        mbar_wait(bfull, 0);
        wg_fence();
        const uint64_t dk = make_desc(base + unit_of(at, 0), 16, 1024);
#pragma unroll
        for (int kk = 0; kk < 8; kk++) mma_rs<0>(s, q[4 * kk], q[4 * kk + 1], q[4 * kk + 2], q[4 * kk + 3], dk + (kk >> 2) * 1024 + (kk & 3) * 2, kk != 0);
        wg_commit();
        bar_arrive(3 - wg, 256);
#pragma unroll
        for (int i = 4; i < 8; i++) stmatrix4((qw + unit_of(qt, 1) + frag_offset(warp)) ^ ((i & 3) << 5), q[4 * i], q[4 * i + 1], q[4 * i + 2], q[4 * i + 3]);
        wg_wait<1>();
        keep(o);
        mbar_arrive_cl(rempty, GE + 16);
        mbar_arrive_cl(rempty, GE + 24);
        store_chunk<0>(o, qw + unit_of(qt, 2) + frag_offset(warp));
        store_chunk<1>(o, qw + unit_of(qt, 3) + frag_offset(warp));
        wg_wait<0>();
        keep(s);
        mbar_arrive_cl(rempty, 0);
      }
      PROF(4, tid == 0 && ps == 1, 61);
      float l0 = 0.f, l1 = 0.f;
      auto step = [&](auto odd_c, const int j, uint32_t (&pw)[32], uint32_t (&pr)[32]) {
        constexpr bool ODD = decltype(odd_c)::value;
        const bool first = !ODD && (j & 2) == 0, last = ODD && j == 7;
        const uint32_t ph = (j >> 1) & 1;
        float i0, i1, a0, a1;
        const bool so = !ODD && j == 4;
        if (so) { i0 = inv_quad_sum(l0); i1 = inv_quad_sum(l1); l0 = 0.f; l1 = 0.f; }
        bool redo = !ODD && (j | ps) == 0;
        while (true) {
          if (redo) {
            float m0 = fmaxf(s[0], s[1]), m1 = fmaxf(s[2], s[3]);
#pragma unroll
            for (int i = 1; i < 16; i++) { m0 = fmaxf(m0, fmaxf(s[4 * i], s[4 * i + 1])); m1 = fmaxf(m1, fmaxf(s[4 * i + 2], s[4 * i + 3])); }
            m0 = fmaxf(m0, __shfl_xor_sync(0xffffffffu, m0, 1)); m1 = fmaxf(m1, __shfl_xor_sync(0xffffffffu, m1, 1));
            m0 = fmaxf(m0, __shfl_xor_sync(0xffffffffu, m0, 2)); m1 = fmaxf(m1, __shfl_xor_sync(0xffffffffu, m1, 2));
            m0 *= SCL2; m1 *= SCL2;
            if (!first) {
              m0 = fmaxf(m0, f0); m1 = fmaxf(m1, f1);
              const float c0 = ex2(f0 - m0), c1 = ex2(f1 - m1);
              l0 *= c0; l1 *= c1;
              wg_wait<0>();
              keep(o);
#pragma unroll
              for (int i = 0; i < 16; i++) { o[4 * i] *= c0; o[4 * i + 1] *= c0; o[4 * i + 2] *= c1; o[4 * i + 3] *= c1; }
            }
            f0 = m0; f1 = m1;
          }
          float b0 = 0.f, b1 = 0.f;
          a0 = 0.f; a1 = 0.f;
#pragma unroll
          for (int i = 0; i < 16; i++) {
            const float e0 = ex2(fmaf(s[4 * i], SCL2, -f0)), e1 = ex2(fmaf(s[4 * i + 1], SCL2, -f0));
            const float e2 = ex2(fmaf(s[4 * i + 2], SCL2, -f1)), e3 = ex2(fmaf(s[4 * i + 3], SCL2, -f1));
            a0 += e0; b0 += e1; a1 += e2; b1 += e3;
            pw[2 * i] = pack_bf(e0, e1); pw[2 * i + 1] = pack_bf(e2, e3);
            if (i == VREL) {
#pragma unroll
              for (int k = 0; k < 2 * VREL + 2; k++) asm volatile("" : "+r"(pw[k])::"memory");
              mbar_wait(bar_mod, 0);
              wg_wait<0>();
              mbar_arrive_cl(rempty, ODD ? 16 : 0, !redo && (ODD || j));
#pragma unroll
              for (int k = 4 * VREL + 4; k < 64; k++) asm volatile("" : "+f"(s[k])::"memory");
            }
          }
          a0 += b0; a1 += b1;
          if (redo) break;
          redo = __any_sync(0xffffffffu, !(a0 + a1 < 0x1p90f));
          if (first) {
            uint32_t m0 = __ballot_sync(0xffffffffu, a0 > 0x1p-80f), m1 = __ballot_sync(0xffffffffu, a1 > 0x1p-80f);
            m0 |= m0 >> 1; m1 |= m1 >> 1; m0 |= m0 >> 2; m1 |= m1 >> 2;
            redo = redo || (m0 & m1 & 0x11111111u) != 0x11111111u;
          }
          if (!redo) break;
        }
        l0 += a0; l1 += a1;
        keep(pw);
        keep(o);
        if (so) store_chunk<0>(o, i0, i1, qw + unit_of(qt, 0) + frag_offset(warp));
        keep(o);
        if (j == (ODD ? 5 : 0)) { fence_async_smem(); if (ODD) mbar_arrive(bar_ofull + wg * 8); }
        mbar_wait(bfull + (ODD ? 24 : 8), ph);
        bar_sync(2 + wg, 256);
        if (!last) {
          const uint32_t qn = qt >> (j >= 3 ? 8 : 0);
          wg_fence();
          issue_qk(s, qw + unit_of(qn, 0), qw + unit_of(qn, 1), base + unit_of(at, ODD ? 3 : 1));
          wg_commit();
          mbar_wait(bfull + (ODD ? 0 : 16), ODD ? ph ^ 1 : ph);
        }
        if (so) { store_chunk<1>(o, i0, i1, qw + unit_of(qt, 1) + frag_offset(warp)); keep(o); }
        wg_fence();
        issue_pv(o, pw, base + unit_of(at, ODD ? (last ? 3 : 0) : 2), !first);
        wg_commit();
        bar_arrive(3 - wg, 256);
        wg_wait<1>();
        keep(s);
        mbar_arrive_cl(rempty, ODD ? 24 : 8, !last);
        PROF(4, tid == 0 && ps == 1, 51 + j);
      };
      uint32_t pa[32], pb[32];
#pragma unroll 1
      for (int j = 0; j < 8; j += 2) {
        step(std::false_type{}, j, pa, pb);
        step(std::true_type{}, j + 1, pb, pa);
      }
      {
        const float i0 = inv_quad_sum(l0), i1 = inv_quad_sum(l1);
        wg_wait<0>();
        keep(o);
        mbar_arrive_cl(rempty, 24);
        store_chunk<0>(o, i0, i1, qw + unit_of(qt, 2) + frag_offset(warp));
        store_chunk<1>(o, i0, i1, qw + unit_of(qt, 3) + frag_offset(warp));
        fence_async_smem();
        mbar_arrive(bar_ofull + 16 + wg * 8);
      }
      PROF(2, tid == 0, 10 + ps * 8);
    }

    const int ln = fresh_lane(), g = ln >> 2, tq = ln & 3, ct = warp * 32 + ln;
    const bool lane0 = ln == 0;
    const int lrow0 = warp * 16 + g;
    const int grow0 = rb * 128 + lrow0;
    const uint32_t res = base + OFF_RES, trow = res + wg * 8192 + frag_offset(warp);
    uint32_t xr[32];
    uint4 sv[4], own;
    uint32_t* sp[4];
#pragma unroll
    for (int k = 0; k < 4; k++) sp[k] = g_stats + ((((tq >> 1) * 4 + k) ^ cj) * SEQ + grow0 + (tq & 1) * 8) * 4;
    {
      const uint64_t da = make_desc(base + wg * 8192, 16, 1024), db = make_desc(base, 8192, 1024);
      constexpr int U = UNIT / 16;
#define HALF_STAGE(acc, xu, wu) _Pragma("unroll") for (int kk = 0; kk < 4; kk++) mma_ss<1>(acc, da + (xu) * U + kk * 2, db + (wu) * U + kk * 128, 1)
      PROF(10, ct == PT, 19); STAMP(0);
      cluster_arrive();
      mbar_wait(gfull, 1);
      mbar_wait(gfull + 8, 1);
      bar_sync(2 + wg, 256);
      wg_fence();
      HALF_STAGE(o, 7, 1);
      HALF_STAGE(o, 8, 3);
      wg_commit();
      STAMP(16);
      mbar_wait(gfull + 16, 1);
      STAMP(17);
      wg_fence();
      HALF_STAGE(o, 6, 11);
      wg_commit();
      bar_arrive(3 - wg, 256);
      mbar_wait(bar_par, 0);
      uint32_t* xo = g_xch + ((size_t)b * 8 * 256 + ct) * 4;
      const uint32_t* xi = g_xch + ((size_t)(b ^ 2) * 8 * 256 + ct) * 4;
      const uint32_t par1 = (~lds1(par + PAR_CONST + 4) & 1) << 16;
      wg_wait<1>();
      mbar_arrive_pred(bar_rel, lane0);
      wg_wait<0>();
      keep(o);
      mbar_arrive_pred(bar_ring, lane0);
      PROF(8, ct == PT, 20); STAMP(1);
#define SEND(i) st_b128(xo + (i) * 1024, (pack_bf(o[8 * (i)], o[8 * (i) + 1]) & ~0x10000u) | par1, pack_bf(o[8 * (i) + 2], o[8 * (i) + 3]), \
                        pack_bf(o[8 * (i) + 4], o[8 * (i) + 5]), pack_bf(o[8 * (i) + 6], o[8 * (i) + 7]))
#pragma unroll
      for (int i = 0; i < NS1; i++) SEND(i);
      PROF(8, ct == PT, 21); STAMP(2);
      bar_sync(2 + wg, 256);
      wg_fence();
      HALF_STAGE(s, 7, 0);
      HALF_STAGE(s, 8, 2);
      HALF_STAGE(s, 6, 10);
      wg_commit();
      bar_arrive(3 - wg, 256);
      STAMP(18);
      mbar_wait(gfull + 24, 1);
#pragma unroll
      for (int i = NS1; i < 8; i++) SEND(i);
      uint4 v[8];
#pragma unroll
      for (int i = 0; i < LD1; i++) v[i] = ld_b128(xi + i * 1024);
      STAMP(19);
      mbar_wait(bar_xres, 0);
      wg_wait<0>();
      mbar_arrive_pred(bar_ring + 8, lane0);
      bar_sync(2 + wg, 256);
      STAMP(20);
#pragma unroll
      for (int i = LD1; i < LD2; i++) v[i] = ld_b128(xi + i * 1024);
      mbar_wait(bar_xres, 0);
      wg_fence();
      HALF_STAGE(s, 9, 4);
      wg_commit();
      mbar_wait(bar_rx, 0);
      wg_fence();
      HALF_STAGE(s, 1, 5);
      wg_commit();
      bar_arrive(3 - wg, 256);
      STAMP(21);
#pragma unroll
      for (int i = LD2; i < 8; i++) v[i] = ld_b128(xi + i * 1024);
      if (LD2 < 8) mbar_wait(bar_xres, 0);
      wg_wait<0>();
      keep(s);
      mbar_arrive_pred(bar_ring + 16, lane0);
      PROF(10, ct == PT, 23); STAMP(4);
#pragma unroll
      for (int i = 0; i < 16; i += 2) ldmatrix4((trow ^ ((i & 7) << 4)) + (i >> 3) * 16384, xr[2 * i], xr[2 * i + 1], xr[2 * i + 2], xr[2 * i + 3]);
      uint32_t ga[16];
      uint4 bw[8];
#pragma unroll
      for (int i = 0; i < 8; i++) {
        if (!(i & 1)) {
          const uint4 t = lds4(par + PAR_SINK + i * 32 + tq * 16);
          ga[2 * i] = t.x; ga[2 * i + 1] = t.y; ga[2 * i + 2] = t.z; ga[2 * i + 3] = t.w;
        }
        bw[i] = lds4(par + PAR_T1 + i * 64 + tq * 16);
        if (!(g & 1)) { bw[i].x = 0x3f803f80u; bw[i].y = 0x3f803f80u; }
      }
      uint32_t pk[32];
      pack_p(s, pk);
      keep(pk);
      {
        uint32_t n = 0, miss;
        do {
          miss = 0;
#pragma unroll
          for (int i = 0; i < 8; i++) miss |= v[i].x ^ par1;
          miss = __any_sync(0xffffffffu, miss & 0x10000u);
          if (miss) {
#pragma unroll
            for (int i = 0; i < 8; i++)
              asm volatile("{ .reg .pred p; .reg .b32 t; xor.b32 t, %0, %5; and.b32 t, t, 0x10000; setp.ne.u32 p, t, 0;\n"
                           "@p ld.relaxed.gpu.global.v4.u32 {%0, %1, %2, %3}, [%4]; }"
                           : "+r"(v[i].x), "+r"(v[i].y), "+r"(v[i].z), "+r"(v[i].w) : "l"(xi + i * 1024), "r"(par1) : "memory");
          }
          watchdog(n);
        } while (miss);
      }
      PROF(8, ct == PT, 22); STAMP(3);
      float ds[4] = {0.f, 0.f, 0.f, 0.f}, dl[4] = {0.f, 0.f, 0.f, 0.f}, q0[4] = {0.f, 0.f, 0.f, 0.f}, q1[4] = {0.f, 0.f, 0.f, 0.f};
#pragma unroll
      for (int i = 0; i < 8; i++) {
        const uint32_t u0 = hfma2(ga[2 * i], hadd2(pk[4 * i], v[i].x & ~0x10000u), xr[4 * i]);
        const uint32_t u1 = hfma2(ga[2 * i], hadd2(pk[4 * i + 1], v[i].y), xr[4 * i + 1]);
        const uint32_t u2 = hfma2(ga[2 * i + 1], hadd2(pk[4 * i + 2], v[i].z), xr[4 * i + 2]);
        const uint32_t u3 = hfma2(ga[2 * i + 1], hadd2(pk[4 * i + 3], v[i].w), xr[4 * i + 3]);
        xr[4 * i] = u0; xr[4 * i + 1] = u1; xr[4 * i + 2] = u2; xr[4 * i + 3] = u3;
        mma16816(ds, u0, u1, u2, u3, bw[i].x, bw[i].y);
        mma16816(dl, u0, u1, u2, u3, bw[i].z, bw[i].w);
        mma16816(q0, u0, u1, u2, u3, u0, u2);
        mma16816(q1, u0, u1, u2, u3, u1, u3);
      }
      const float sqa = __shfl_sync(0xffffffffu, (g & 1) ? q0[1] : q0[0], g * 4 + (g >> 1));
      const float sqb = __shfl_sync(0xffffffffu, (g & 1) ? q1[3] : q1[2], g * 4 + (g >> 1));
      own = (tq & 1) ? make_uint4(__float_as_uint(ds[2]), __float_as_uint(sqb), __float_as_uint(ds[3] + dl[3]), tag)
                                 : make_uint4(__float_as_uint(ds[0]), __float_as_uint(sqa), __float_as_uint(ds[1] + dl[1]), tag);
      if (tq < 2) st_b128(sp[0], own.x, own.y, own.z, own.w);
#pragma unroll
      for (int k = 0; k < 4; k++) sv[k] = make_uint4(0, 0, 0, 0);
    }
    PROF(8, ct == PT, 29); STAMP(5);
    uint32_t mm, ih, il;
    float rbest;
    uint32_t wf[128];
    const uint32_t frow = (ln & 7) + (ln >> 4) * 8;
    const uint32_t wfo = base + (warp & 1) * 8192 + frow * 64 + ((((ln >> 3) & 1) ^ ((frow >> 1) & 3)) << 4);
#define LOAD_WF(m) _Pragma("unroll") for (int f = 0; f < 16; f++) {                                                   \
      const int r = ((f >> 1) * 4 + (m) * 2 + (f & 1)) * 4;                                                           \
      ldmatrix4t(((wfo + unit_of((m) ? FT_U : FT_G, warp >> 1)) ^ ((f & 1) * 32)) + (f >> 1) * 1024, wf[r], wf[r + 1], wf[r + 2], wf[r + 3]); \
    }
    bool early;
    {
#pragma unroll
      for (int i = 0; i < 16; i += 2) stmatrix4((trow ^ ((i & 7) << 4)) + (i >> 3) * 16384, xr[2 * i], xr[2 * i + 1], xr[2 * i + 2], xr[2 * i + 3]);
      const uint4 cst = lds4(par + PAR_CONST);
      const float A1 = __uint_as_float(cst.x), A2 = __uint_as_float(cst.z);
      uint32_t n = 0;
      early = false;
#pragma unroll 1
      while (true) {
        uint32_t miss;
        asm volatile("{ .reg .pred p0, p1, p2, p3; .reg .b64 u, v; .reg .b128 w;\n"
                     "setp.ge.u32 p0, %22, 2; setp.ne.and.u32 p0, %4, %21, p0; setp.ne.u32 p1, %8, %21; setp.ne.u32 p2, %12, %21; setp.ne.u32 p3, %16, %21;\n"
                     "@p0 ld.relaxed.gpu.global.v4.u32 {%1, %2, %3, %4}, [%17];\n"
                     "@p1 ld.relaxed.gpu.global.v4.u32 {%5, %6, %7, %8}, [%18];\n"
                     "@p2 ld.relaxed.gpu.global.v4.u32 {%9, %10, %11, %12}, [%19];\n"
                     "@p3 ld.relaxed.gpu.global.v4.u32 {%13, %14, %15, %16}, [%20];\n"
                     "or.pred p0, p0, p1; or.pred p2, p2, p3; or.pred p0, p0, p2; vote.sync.any.pred p0, p0, 0xffffffff; selp.u32 %0, 1, 0, p0; }"
                     : "=r"(miss), "+r"(sv[0].x), "+r"(sv[0].y), "+r"(sv[0].z), "+r"(sv[0].w), "+r"(sv[1].x), "+r"(sv[1].y), "+r"(sv[1].z), "+r"(sv[1].w),
                       "+r"(sv[2].x), "+r"(sv[2].y), "+r"(sv[2].z), "+r"(sv[2].w), "+r"(sv[3].x), "+r"(sv[3].y), "+r"(sv[3].z), "+r"(sv[3].w)
                     : "l"(sp[0]), "l"(sp[1]), "l"(sp[2]), "l"(sp[3]), "r"(tag), "r"(tq) : "memory");
        if (!miss) break;
        if (!early && (b >= NFFN || __all_sync(0xffffffffu, mbar_test(bar_box + (warp >> 1) * 8, 0)))) {
          early = true;
          LOAD_WF(0);
          __syncwarp();
          mbar_arrive_pred(bar_gate, lane0);
        }
        watchdog(n);
      }
      const uint4 v0 = tq < 2 ? own : sv[0], v1 = sv[1], v2 = sv[2], v3 = sv[3];
      PROF(8, ct == PT, 30); STAMP(6);
      float su = (__uint_as_float(v0.x) + __uint_as_float(v1.x)) + (__uint_as_float(v2.x) + __uint_as_float(v3.x));
      float sq = (__uint_as_float(v0.y) + __uint_as_float(v1.y)) + (__uint_as_float(v2.y) + __uint_as_float(v3.y));
      float dt = (__uint_as_float(v0.z) + __uint_as_float(v1.z)) + (__uint_as_float(v2.z) + __uint_as_float(v3.z));
      su += __shfl_xor_sync(0xffffffffu, su, 2); sq += __shfl_xor_sync(0xffffffffu, sq, 2); dt += __shfl_xor_sync(0xffffffffu, dt, 2);
      const float m = su * (1.f / DM);
      float mb, sd;
      ln_scalars(m, fmaxf(sq * (1.f / DM) - m * m, 0.f), mb, sd);
      const float inv = rcp(sd);
      rbest = (dt - mb * A1) * inv + A2;
      mm = pack_bf(mb, mb);
      ih = pack_bf(inv, inv);
      const float lo = inv - bf_lo(ih);
      il = pack_bf(lo, lo);
    }
    int ibest;
    {
      const uint32_t bits = __float_as_uint(rbest);
      const uint32_t key = (((int)bits < 0 ? ~bits : bits | 0x80000000u) & ~0x1ffu) | ((127 - lrow0 - (tq & 1) * 8) << 2) | tag;
      sts1(par + PAR_RED + warp * 4, __reduce_max_sync(0xffffffffu, key));
      PROF(8, ct == PT, 38); STAMP(7);
      bar_sync(1, 256);
      const uint4 ka = lds4(par + PAR_RED), kb = lds4(par + PAR_RED + 16);
      const uint32_t k2 = max(max(max(ka.x, ka.y), max(ka.z, ka.w)), max(max(kb.x, kb.y), max(kb.z, kb.w)));
      if (ct < CR && cj == 0) st_relaxed(g_cand + ct * 512 + rb * CS, k2);
      ibest = 127 - ((k2 >> 2) & 127);
    }
    PROF(8, ct == PT, 39); STAMP(8);
    if ((ibest >> 4) == warp) {
      const int src = (ibest & 7) * 4 + ((ibest >> 3) & 1), ch = g * 2;
      const uint32_t cm = __shfl_sync(0xffffffffu, mm, src), ch_ = __shfl_sync(0xffffffffu, ih, src), cl = __shfl_sync(0xffffffffu, il, src);
      const uint32_t xa = res + (ch >> 3) * 16384 + ibest * 128 + (((ch & 7) ^ (ibest & 7)) << 4) + tq * 4;
      const uint32_t x0 = lds1(xa), x1 = lds1(xa ^ 16);
      const uint2 p0 = lds2(par + PAR_T2 + ch * 64 + tq * 16), p1 = lds2(par + PAR_T2 + ch * 64 + 64 + tq * 16);
      uint32_t* dst = g_row + rb * 2 * DM + cj * 128 + ln * 4;
      st_pairs(dst, ln_mod(x0, cm, ch_, cl, p0.x, p0.y), ln_mod(x1, cm, ch_, cl, p1.x, p1.y), tag);
      st_pairs(dst + DM, x0, x1, tag);
      __syncwarp();
    }
    PROF(8, ct == PT, 37); STAMP(9);
    uint32_t wd[64];
    const uint32_t wda = base + unit_of(FT_D, warp >> 1) + (warp & 1) * 8192 + frow * 128 + ((((ln >> 3) & 1) ^ (ln & 7)) << 4);
#define LOAD_WD(f) ldmatrix4t((wda ^ ((((f) >> 1) & 3) * 32)) + ((f) >> 3) * 4096 + ((f) & 1) * 2048, wd[4 * (f)], wd[4 * (f) + 1], wd[4 * (f) + 2], wd[4 * (f) + 3])
    if (!early) {
      if (b < NFFN) mbar_wait(bar_box + (warp >> 1) * 8, 0);
      LOAD_WF(0);
      __syncwarp();
      mbar_arrive_pred(bar_gate, lane0);
    }
    if (b < NFFN) {
      const uint32_t own = base + unit_of(FT_G, warp >> 1) + (warp & 1) * 8192;
      mbar_wait(bar_box + (4 + (warp >> 1)) * 8, 0);
      LOAD_WF(1);
      uint32_t* const ydst = ypart_slot(b, warp * 16 + (tq & 1) * 8 + g);
      PROF(8, ct == PT, 31); STAMP(10);
      bool wdok;
      {
        uint32_t n = 0;
        while (!(wdok = __all_sync(0xffffffffu, mbar_test(bar_box + (8 + (warp >> 1)) * 8, 0))) && !__all_sync(0xffffffffu, mbar_test(bar_sel, 0))) watchdog(n);
      }
      if (wdok) {
#pragma unroll
        for (int f = 0; f < 16; f++) LOAD_WD(f);
      }
      STAMP(11);
      mbar_wait(bar_sel, 0);
      PROF(8, ct == PT, 33); STAMP(12);
      float d[8][4];
#pragma unroll
      for (int i = 0; i < 4; i++) { d[i][0] = 0.f; d[i][1] = 0.f; d[i][2] = 0.f; d[i][3] = 0.f; }
#pragma unroll
      for (int ks = 0; ks < 8; ks++) {
        const uint2 hb = lds2(own + 256 + ks * 32 + tq * 8);
#pragma unroll
        for (int mt = 0; mt < 4; mt++) {
          const int r = ks * 16 + mt * 4;
          mma16816(d[mt], wf[r], wf[r + 1], wf[r + 2], wf[r + 3], hb.x, hb.y);
        }
      }
      sts2(own + (tq * 8 + g) * 8, __float_as_uint((tq & 2) ? ((tq & 1) ? d[1][2] : d[1][0]) : ((tq & 1) ? d[0][2] : d[0][0])),
           __float_as_uint((tq & 2) ? ((tq & 1) ? d[3][2] : d[3][0]) : ((tq & 1) ? d[2][2] : d[2][0])));
      bar_sync(1, 256);
      uint32_t ab[4];
      {
        float G = 0.f, U = 0.f;
        uint2 pv[8];
#pragma unroll
        for (int w8 = 0; w8 < 8; w8++) pv[w8] = lds2(base + ln * 8 + ((FT_G >> (w8 >> 1) * 4) & 15) * UNIT + (w8 & 1) * 8192);
#pragma unroll
        for (int w8 = 0; w8 < 8; w8 += 2) {
          G += __uint_as_float(pv[w8].x) + __uint_as_float(pv[w8 + 1].x);
          U += __uint_as_float(pv[w8].y) + __uint_as_float(pv[w8 + 1].y);
        }
        const float act = rbf(silu_f(rbf(G))) * rbf(U);
        const uint32_t pk = pack_bf(act, __shfl_down_sync(0xffffffffu, act, 1));
#pragma unroll
        for (int i = 0; i < 4; i++) ab[i] = __shfl_sync(0xffffffffu, pk, i * 8 + tq * 2);
      }
      if (!wdok) {
        mbar_wait(bar_box + (8 + (warp >> 1)) * 8, 0);
#pragma unroll
        for (int f = 0; f < 16; f++) LOAD_WD(f);
      }
      PROF(8, ct == PT, 34); STAMP(13);
#pragma unroll
      for (int mt = 0; mt < 8; mt++) {
        d[mt][0] = 0.f; d[mt][1] = 0.f; d[mt][2] = 0.f; d[mt][3] = 0.f;
        mma16816(d[mt], wd[mt * 8], wd[mt * 8 + 1], wd[mt * 8 + 2], wd[mt * 8 + 3], ab[0], ab[1]);
        mma16816(d[mt], wd[mt * 8 + 4], wd[mt * 8 + 5], wd[mt * 8 + 6], wd[mt * 8 + 7], ab[2], ab[3]);
      }
      uint32_t yw[4];
#pragma unroll
      for (int i = 0; i < 4; i++) yw[i] = (tq & 1) ? pack_bf(d[2 * i][2], d[2 * i + 1][2]) : pack_bf(d[2 * i][0], d[2 * i + 1][0]);
      if (tq < 2) st_b128(ydst, (yw[0] & ~1u) | (tag & 1), (yw[1] & ~1u) | (tag >> 1), yw[2], yw[3]);
      PROF(8, ct == PT, 35); STAMP(14);
    }
    mbar_wait(bar_sel, 0);
    mbar_arrive_pred(bar_win, ct == 0);
    const int iwin = lds1(par + PAR_CONST + 60) & 0x7ff;
    const bool cand = (iwin >> 4) == rb * 8 + warp;
    {
      const uint32_t mm0 = __shfl_sync(0xffffffffu, mm, ln & ~1), mm1 = __shfl_sync(0xffffffffu, mm, ln | 1);
      const uint32_t ih0 = __shfl_sync(0xffffffffu, ih, ln & ~1), ih1 = __shfl_sync(0xffffffffu, ih, ln | 1);
      const uint32_t il0 = __shfl_sync(0xffffffffu, il, ln & ~1), il1 = __shfl_sync(0xffffffffu, il, ln | 1);
#pragma unroll OUR
      for (int hf = 0; hf < 2; hf++) {
        uint32_t x[16];
#pragma unroll
        for (int i = 0; i < 8; i += 2) ldmatrix4((trow ^ (i << 4)) + hf * 16384, x[2 * i], x[2 * i + 1], x[2 * i + 2], x[2 * i + 3]);
#pragma unroll
        for (int i = 0; i < 8; i++) {
          const uint4 pv = lds4(par + PAR_T2 + (hf * 8 + i) * 64 + tq * 16);
          x[2 * i] = hfma2(hfma2(ln_norm(x[2 * i], mm0, ih0, il0), pv.x, pv.y), pv.z, x[2 * i]);
          x[2 * i + 1] = hfma2(hfma2(ln_norm(x[2 * i + 1], mm1, ih1, il1), pv.x, pv.y), pv.z, x[2 * i + 1]);
        }
#pragma unroll
        for (int i = 0; i < 8; i += 2) stmatrix4((trow ^ (i << 4)) + hf * 16384, x[2 * i], x[2 * i + 1], x[2 * i + 2], x[2 * i + 3]);
        if (!cand) fence_async_smem();
        __syncwarp();
        if (!cand && elect_one()) {
          tma2d_store(&maps.out, res + hf * 16384 + warp * 2048, cj * 128 + hf * 64, rb * 128 + warp * 16);
          asm volatile("cp.async.bulk.commit_group;" ::: "memory");
        }
      }
    }
    if (cand) {
      const int wrow0 = warp * 16;
#pragma unroll 2
      for (int p = 0; p < 8; p++) {
        const int row = 2 * p + (ln >> 4), ch = ln & 15;
        const uint4 v = lds4(res + (ch >> 3) * 16384 + (wrow0 + row) * 128 + (((ch & 7) ^ (row & 7)) << 4));
        if (rb * 128 + wrow0 + row != iwin) *reinterpret_cast<uint4*>(P.out + (size_t)(rb * 128 + wrow0 + row) * DM + cj * 128 + ch * 8) = v;
      }
    }
    asm volatile("cp.async.bulk.wait_group.read 0;" ::: "memory");
    PROF(8, ct == PT, 11); STAMP(15);
    cluster_wait();
  }
}

typedef CUresult (*EncodeFn)(CUtensorMap*, CUtensorMapDataType, cuuint32_t, void*, const cuuint64_t*, const cuuint64_t*,
                             const cuuint32_t*, const cuuint32_t*, CUtensorMapInterleave, CUtensorMapSwizzle,
                             CUtensorMapL2promotion, CUtensorMapFloatOOBfill);

void map2d(EncodeFn enc, CUtensorMap* m, const void* p, uint64_t rows, uint64_t cols, uint32_t brows) {
  cuuint64_t dims[2] = {cols, rows}, strides[1] = {cols * 2};
  cuuint32_t box[2] = {64, brows}, es[2] = {1, 1};
  enc(m, CU_TENSOR_MAP_DATA_TYPE_BFLOAT16, 2, const_cast<void*>(p), dims, strides, box, es, CU_TENSOR_MAP_INTERLEAVE_NONE,
      CU_TENSOR_MAP_SWIZZLE_128B, CU_TENSOR_MAP_L2_PROMOTION_L2_256B, CU_TENSOR_MAP_FLOAT_OOB_FILL_NONE);
}
void map2d_narrow(EncodeFn enc, CUtensorMap* m, const void* p, uint64_t rows, uint64_t cols, uint32_t brows) {
  cuuint64_t dims[2] = {cols, rows}, strides[1] = {cols * 2};
  cuuint32_t box[2] = {32, brows}, es[2] = {1, 1};
  enc(m, CU_TENSOR_MAP_DATA_TYPE_BFLOAT16, 2, const_cast<void*>(p), dims, strides, box, es, CU_TENSOR_MAP_INTERLEAVE_NONE,
      CU_TENSOR_MAP_SWIZZLE_64B, CU_TENSOR_MAP_L2_PROMOTION_L2_64B, CU_TENSOR_MAP_FLOAT_OOB_FILL_NONE);
}
void map3d(EncodeFn enc, CUtensorMap* m, const void* p, uint64_t rows, uint64_t cols, uint32_t brows, uint32_t nch) {
  cuuint64_t dims[3] = {64, rows, cols / 64}, strides[2] = {cols * 2, 128};
  cuuint32_t box[3] = {64, brows, nch}, es[3] = {1, 1, 1};
  enc(m, CU_TENSOR_MAP_DATA_TYPE_BFLOAT16, 3, const_cast<void*>(p), dims, strides, box, es, CU_TENSOR_MAP_INTERLEAVE_NONE,
      CU_TENSOR_MAP_SWIZZLE_128B, CU_TENSOR_MAP_L2_PROMOTION_L2_256B, CU_TENSOR_MAP_FLOAT_OOB_FILL_NONE);
}

}

extern "C" void kernel_launch(void* const* d_in, const int* in_sizes, int n_in, void* d_out, int out_size) {
  (void)in_sizes; (void)n_in; (void)out_size;
  static EncodeFn enc = nullptr;
  if (!enc) {
    void* fn = nullptr;
    cudaDriverEntryPointQueryResult st;
    cudaGetDriverEntryPoint("cuTensorMapEncodeTiled", &fn, cudaEnableDefault, &st);
    enc = (EncodeFn)fn;
    cudaFuncSetAttribute(fused_kernel, cudaFuncAttributeMaxDynamicSharedMemorySize, SMEM_BYTES);
  }
  Maps maps;
  map2d(enc, &maps.x, d_in[0], SEQ, DM, 128);
  map2d(enc, &maps.out, d_out, SEQ, DM, 16);
  map3d(enc, &maps.wq, d_in[3], DM, NQ, 64, 2);
  map3d(enc, &maps.k, d_in[1], 4 * SK, 128, 128, 1);
  map3d(enc, &maps.v, d_in[2], 4 * SK, 128, 128, 1);
  map3d(enc, &maps.wo, d_in[4], NQ, DM, 64, 2);
  map2d_narrow(enc, &maps.wg, d_in[7], DM, FF, 256);
  map2d_narrow(enc, &maps.wu, d_in[8], DM, FF, 256);
  map3d(enc, &maps.wd, d_in[9], FF, DM, 32, 4);
  map2d_narrow(enc, &maps.wm, d_in[11], DM, NMOD, 256);
  Ptrs p;
  p.x = (const __nv_bfloat16*)d_in[0];
  p.w_r = (const __nv_bfloat16*)d_in[6];
  p.w_gate = (const __nv_bfloat16*)d_in[7];
  p.w_up = (const __nv_bfloat16*)d_in[8];
  p.w_down = (const __nv_bfloat16*)d_in[9];
  p.c = (const __nv_bfloat16*)d_in[10];
  p.w_mod = (const __nv_bfloat16*)d_in[11];
  p.out = (__nv_bfloat16*)d_out;
  fused_kernel<<<NMAIN + NHELP, 384, SMEM_BYTES>>>(maps, p);
}
```

```cpp
#include <cuda_runtime.h>
#include <cuda_bf16.h>
#include <cuda.h>
#include <stdint.h>
#include <type_traits>

#define HD 2
#define HDX 2
#define NRS 8
#define FPACE 3
#define GOST 20
#define WB 2
#define WN 20
#define RES0 17
#define RES1 20
#define HU 32
#define NS1 5
#define PG0 15
#define FB0 0
#define FB2 8
#define OPS 8192
#define OFL 0
#define ODS 8
#define MODUL hfma2
#define ODS1 5
#define LD1 0
#define LD2 4
#define FB1 2
#define FPB 8
#define FPACE0 2
#define OSL 900
#define OSL2 400
#define CR 8
#define CS 8
#define OURV 1
#define VREL 5
#define E0 3

namespace {

constexpr int SEQ = 2048, DM = 1024, NQ = 4096, SK = 2048, WIN = 512, FF = 3584, NMOD = 6144;
constexpr int OUR = OURV;
constexpr int NMAIN = 128, NHELP = 4, NFFN = 112;
constexpr int NSLOT = 4, SLOT_BYTES = 32768, UNIT = 16384, GST_BYTES = 3 * UNIT;
constexpr uint32_t XT1 = 0xDCBA, XT2 = 0x9687, XT2B = 0x96DC;
constexpr uint32_t WT0 = 0xA741, WT1 = 0x7420, WT2 = 0x4A20;
constexpr uint32_t AT0 = WT1, AT1 = WT2;
constexpr uint32_t QT = 0xDC9696DC;
constexpr int OFF_STAGE = 12 * UNIT;
constexpr uint32_t FT_G = 0x07B3, FT_U = 0xA628, FT_D = 0x5149;
constexpr int OFF_RES = 12 * UNIT;
constexpr int OFF_PAR = 14 * UNIT;
constexpr int OFF_BAR = OFF_PAR + 2528;
constexpr int SMEM_BYTES = OFF_BAR + 544;
static_assert(SMEM_BYTES <= 232448, "smem");

constexpr int PAR_T1 = 0;
constexpr int PAR_T2 = 512;
constexpr int PAR_CONST = 1536;
constexpr int PAR_RED = 1600;
constexpr int PAR_SINK = 2176;

struct Maps {
  CUtensorMap x, wq, k, v, wo, wg, wu, wd, wm, out;
};
struct Ptrs {
  const __nv_bfloat16 *x, *w_r, *c, *w_mod, *w_gate, *w_up, *w_down;
  __nv_bfloat16* out;
};

__device__ __align__(1024) uint8_t g_act[16 * 80 * UNIT];
__device__ __align__(128) uint32_t g_mod[NMOD];
__device__ __align__(128) uint32_t g_modp[2 * 2 * DM];
__device__ __align__(128) uint32_t g_ln1[SEQ * 4];
__device__ __align__(128) uint32_t g_cnt_h[16 * 32];
__device__ __align__(128) uint32_t g_cnt_o[128 * 32];
__device__ __align__(128) uint32_t g_xch[NMAIN * 8 * 256 * 4];
__device__ __align__(128) uint32_t g_stats[8 * SEQ * 4];
__device__ __align__(128) uint32_t g_cand[CR * 512];
__device__ __align__(128) uint32_t g_row[16 * 2 * DM];
__device__ __align__(128) uint32_t g_ypart[NMAIN * NFFN * 4];
__device__ __forceinline__ uint32_t* ypart_slot(int writer, int reader) { return g_ypart + (writer * NMAIN + reader) * 4; }
__device__ uint32_t g_epoch;

__device__ __forceinline__ uint32_t fresh_lane() { uint32_t l; asm volatile("mov.u32 %0, %%laneid;" : "=r"(l)); return l; }
__device__ __forceinline__ uint32_t frag_offset(int warp) {
  const uint32_t l = fresh_lane();
  return ((warp & 3) * 16 + (l & 15)) * 128 + (((l >> 4) ^ (l & 7)) << 4);
}
__device__ __forceinline__ bool elect_one() {
  uint32_t p;
  asm volatile("{ .reg .pred q; elect.sync _|q, 0xffffffff; selp.u32 %0, 1, 0, q; }" : "=r"(p));
  return p;
}
__device__ __forceinline__ uint32_t smem_u32(const void* p) { return (uint32_t)__cvta_generic_to_shared(p); }
__device__ __forceinline__ void mbar_init(uint32_t bar, uint32_t cnt) {
  asm volatile("mbarrier.init.shared::cta.b64 [%0], %1;" ::"r"(bar), "r"(cnt) : "memory");
}
__device__ __forceinline__ void mbar_expect_tx(uint32_t bar, uint32_t bytes) {
  asm volatile("mbarrier.arrive.expect_tx.shared::cta.b64 _, [%0], %1;" ::"r"(bar), "r"(bytes) : "memory");
}
__device__ __forceinline__ void mbar_arrive(uint32_t bar) {
  asm volatile("mbarrier.arrive.shared::cta.b64 _, [%0];" ::"r"(bar) : "memory");
}
__device__ __forceinline__ void mbar_arrive_pred(uint32_t bar, bool p) {
  asm volatile("{ .reg .pred p; setp.ne.b32 p, %1, 0; @p mbarrier.arrive.shared::cta.b64 _, [%0]; }" ::"r"(bar), "r"((int)p) : "memory");
}
__device__ __forceinline__ void mbar_arrive_cl(uint32_t bar, uint32_t off, bool p = true) {
  asm volatile("{ .reg .pred p, q; .reg .b32 a; setp.ne.b32 q, %2, 0; setp.ne.and.b32 p, %0, 0, q; add.u32 a, %0, %1; @p mbarrier.arrive.shared::cluster.b64 _, [a]; }"
               ::"r"(bar), "r"(off), "r"((int)p) : "memory");
}
__device__ __forceinline__ uint32_t mapa(uint32_t addr, uint32_t cta) {
  uint32_t r; asm("mapa.shared::cluster.u32 %0, %1, %2;" : "=r"(r) : "r"(addr), "r"(cta)); return r;
}
__device__ __forceinline__ void cluster_arrive() { asm volatile("barrier.cluster.arrive.relaxed.aligned;" ::: "memory"); }
__device__ __forceinline__ void cluster_wait() { asm volatile("barrier.cluster.wait.aligned;" ::: "memory"); }
__device__ __forceinline__ void watchdog(uint32_t& n) {
}
__device__ __forceinline__ void mbar_wait(uint32_t bar, uint32_t parity) {
  asm volatile("{\n.reg .pred p;\nWAIT_%=:\nmbarrier.try_wait.parity.shared::cta.b64 p, [%0], %1;\n@!p bra WAIT_%=;\n}" ::"r"(bar), "r"(parity) : "memory");
}
__device__ __forceinline__ bool mbar_test(uint32_t bar, uint32_t parity) {
  uint32_t ok;
  asm volatile("{\n.reg .pred p;\nmbarrier.test_wait.parity.shared::cta.b64 p, [%1], %2;\nselp.u32 %0, 1, 0, p;\n}" : "=r"(ok) : "r"(bar), "r"(parity) : "memory");
  return ok;
}
__device__ __forceinline__ uint64_t l2_stream() {
  uint64_t f; asm("createpolicy.fractional.L2::evict_first.b64 %0, 1.0;" : "=l"(f)); return f;
}
__device__ __forceinline__ void tma2d(uint32_t dst, const CUtensorMap* m, int c0, int c1, uint32_t bar) {
  asm volatile("cp.async.bulk.tensor.2d.shared::cluster.global.mbarrier::complete_tx::bytes.L2::cache_hint [%0], [%1, {%3, %4}], [%2], %5;"
               ::"r"(dst), "l"(m), "r"(bar), "r"(c0), "r"(c1), "l"(l2_stream()) : "memory");
}
__device__ __forceinline__ void bulk_load(uint32_t dst, const void* src, uint32_t bytes, uint32_t bar) {
  asm volatile("cp.async.bulk.shared::cluster.global.mbarrier::complete_tx::bytes [%0], [%1], %2, [%3];" ::"r"(dst), "l"(src), "r"(bytes), "r"(bar) : "memory");
}
__device__ __forceinline__ void bulk_load_stream(uint32_t dst, const void* src, uint32_t bytes, uint32_t bar) {
  asm volatile("cp.async.bulk.shared::cluster.global.mbarrier::complete_tx::bytes.L2::cache_hint [%0], [%1], %2, [%3], %4;"
               ::"r"(dst), "l"(src), "r"(bytes), "r"(bar), "l"(l2_stream()) : "memory");
}
__device__ __forceinline__ void tma2d_store(const CUtensorMap* m, uint32_t src, int c0, int c1) {
  asm volatile("cp.async.bulk.tensor.2d.global.shared::cta.bulk_group [%0, {%2, %3}], [%1];" ::"l"(m), "r"(src), "r"(c0), "r"(c1) : "memory");
}
__device__ __forceinline__ void bulk_store(void* dst, uint32_t src, uint32_t bytes) {
  asm volatile("cp.async.bulk.global.shared::cta.bulk_group [%0], [%1], %2;" ::"l"(dst), "r"(src), "r"(bytes) : "memory");
}
__device__ __forceinline__ int slice_of(int i) { return i + ((i & 7) == 1) - ((i & 7) == 2); }
__device__ __forceinline__ int otile_of(int i, int cj) {
  const int h = (0xFB7EA6D951C84320ull >> (i >> 1) * 4) & 15, r = h >> 2, a0 = cj >> 1;
  const int a = (h & 2) ? (r ? r - (r <= a0) : a0) : r;
  return ((2 * a + (cj & 1)) * 4 + (h & 3)) * 2 + (i & 1);
}
__device__ __forceinline__ uint32_t unit_of(uint32_t table, uint32_t i) { return ((table >> (i * 4)) & 15) * UNIT; }
__device__ __forceinline__ void tma3d(uint32_t dst, const CUtensorMap* m, int c0, int c1, int c2, uint32_t bar) {
  asm volatile("cp.async.bulk.tensor.3d.shared::cluster.global.mbarrier::complete_tx::bytes.L2::cache_hint [%0], [%1, {%3, %4, %5}], [%2], %6;"
               ::"r"(dst), "l"(m), "r"(bar), "r"(c0), "r"(c1), "r"(c2), "l"(l2_stream()) : "memory");
}
template <bool STREAM>
__device__ __forceinline__ void tma3d_mc(uint32_t dst, const CUtensorMap* m, int c0, int c1, int c2, uint32_t bar) {
  if (STREAM)
    asm volatile("cp.async.bulk.tensor.3d.shared::cluster.global.mbarrier::complete_tx::bytes.multicast::cluster.L2::cache_hint [%0], [%1, {%3, %4, %5}], [%2], %6, %7;"
                 ::"r"(dst), "l"(m), "r"(bar), "r"(c0), "r"(c1), "r"(c2), "h"((uint16_t)3), "l"(l2_stream()) : "memory");
  else
    asm volatile("cp.async.bulk.tensor.3d.shared::cluster.global.mbarrier::complete_tx::bytes.multicast::cluster [%0], [%1, {%3, %4, %5}], [%2], %6;"
                 ::"r"(dst), "l"(m), "r"(bar), "r"(c0), "r"(c1), "r"(c2), "h"((uint16_t)3) : "memory");
}
__device__ __forceinline__ void prefetch_map(const CUtensorMap* m) {
  asm volatile("prefetch.tensormap [%0];" ::"l"(m) : "memory");
}
__device__ __forceinline__ void fence_async() { asm volatile("fence.proxy.async.global;" ::: "memory"); }
__device__ __forceinline__ void fence_async_smem() { asm volatile("fence.proxy.async.shared::cta;" ::: "memory"); }
__device__ __forceinline__ void bar_sync(int id, int n) { asm volatile("bar.sync %0, %1;" ::"r"(id), "r"(n) : "memory"); }
__device__ __forceinline__ void bar_arrive(int id, int n) { asm volatile("bar.arrive %0, %1;" ::"r"(id), "r"(n) : "memory"); }
__device__ __forceinline__ void wg_fence() { asm volatile("wgmma.fence.sync.aligned;" ::: "memory"); }
__device__ __forceinline__ void wg_commit() { asm volatile("wgmma.commit_group.sync.aligned;" ::: "memory"); }
template <int N> __device__ __forceinline__ void wg_wait() { asm volatile("wgmma.wait_group.sync.aligned %0;" ::"n"(N) : "memory"); }
__device__ __forceinline__ uint64_t make_desc(uint32_t addr, uint32_t lbo, uint32_t sbo) {
  return (uint64_t)((addr & 0x3FFFF) >> 4) | ((uint64_t)(lbo >> 4) << 16) | ((uint64_t)(sbo >> 4) << 32) | (1ull << 62);
}
__device__ __forceinline__ uint32_t ld_relaxed(const uint32_t* p) {
  uint32_t v; asm volatile("ld.relaxed.gpu.global.u32 %0, [%1];" : "=r"(v) : "l"(p) : "memory"); return v;
}
__device__ __forceinline__ uint32_t ld_acquire(const uint32_t* p) {
  uint32_t v; asm volatile("ld.acquire.gpu.global.u32 %0, [%1];" : "=r"(v) : "l"(p) : "memory"); return v;
}
__device__ __forceinline__ uint4 ld_relaxed4(const uint32_t* p) {
  uint4 v; asm volatile("ld.relaxed.gpu.global.v4.u32 {%0,%1,%2,%3}, [%4];" : "=r"(v.x), "=r"(v.y), "=r"(v.z), "=r"(v.w) : "l"(p) : "memory"); return v;
}
__device__ __forceinline__ uint2 ld_relaxed2(const uint32_t* p) {
  uint2 v; asm volatile("ld.relaxed.gpu.global.v2.u32 {%0,%1}, [%2];" : "=r"(v.x), "=r"(v.y) : "l"(p) : "memory"); return v;
}
__device__ __forceinline__ void st_relaxed(uint32_t* p, uint32_t v) {
  asm volatile("st.relaxed.gpu.global.u32 [%0], %1;" ::"l"(p), "r"(v) : "memory");
}
__device__ __forceinline__ void st_relaxed2(uint32_t* p, uint32_t a, uint32_t b) {
  asm volatile("st.relaxed.gpu.global.v2.u32 [%0], {%1,%2};" ::"l"(p), "r"(a), "r"(b) : "memory");
}
__device__ __forceinline__ void st_relaxed4(uint32_t* p, uint32_t a, uint32_t b, uint32_t c, uint32_t d) {
  asm volatile("st.relaxed.gpu.global.v4.u32 [%0], {%1,%2,%3,%4};" ::"l"(p), "r"(a), "r"(b), "r"(c), "r"(d) : "memory");
}
__device__ __forceinline__ void st_b128(uint32_t* p, uint32_t a, uint32_t b, uint32_t c, uint32_t d) {
  asm volatile("{ .reg .b64 u, v; .reg .b128 w; mov.b64 u, {%1, %2}; mov.b64 v, {%3, %4}; mov.b128 w, {u, v}; st.relaxed.gpu.global.b128 [%0], w; }"
               ::"l"(p), "r"(a), "r"(b), "r"(c), "r"(d) : "memory");
}
__device__ __forceinline__ uint4 ld_b128(const uint32_t* p) {
  uint4 r;
  asm volatile("{ .reg .b64 u, v; .reg .b128 w; ld.relaxed.gpu.global.b128 w, [%4]; mov.b128 {u, v}, w; mov.b64 {%0, %1}, u; mov.b64 {%2, %3}, v; }"
               : "=r"(r.x), "=r"(r.y), "=r"(r.z), "=r"(r.w) : "l"(p) : "memory");
  return r;
}
__device__ __forceinline__ void st_pairs(uint32_t* p, uint32_t a, uint32_t b, uint32_t tag) {
  asm volatile("{ .reg .b64 u, v; mov.b64 u, {%1, %3}; mov.b64 v, {%2, %3}; st.relaxed.gpu.global.v2.b64 [%0], {u, v}; }"
               ::"l"(p), "r"(a), "r"(b), "r"(tag) : "memory");
}
__device__ __forceinline__ uint4 ld_pairs(const uint32_t* p) {
  uint4 v;
  asm volatile("{ .reg .b64 u, v; ld.relaxed.gpu.global.v2.b64 {u, v}, [%4]; mov.b64 {%0, %1}, u; mov.b64 {%2, %3}, v; }"
               : "=r"(v.x), "=r"(v.y), "=r"(v.z), "=r"(v.w) : "l"(p) : "memory");
  return v;
}
__device__ __forceinline__ uint2 ld_pair(const uint32_t* p) {
  uint2 v;
  asm volatile("{ .reg .b64 u; ld.relaxed.gpu.global.b64 u, [%2]; mov.b64 {%0, %1}, u; }" : "=r"(v.x), "=r"(v.y) : "l"(p) : "memory");
  return v;
}
__device__ __forceinline__ void red_release(uint32_t* p, uint32_t v) {
  asm volatile("red.release.gpu.global.add.u32 [%0], %1;" ::"l"(p), "r"(v) : "memory");
}
__device__ __forceinline__ uint32_t ldg_nc1(const void* p) {
  uint32_t v;
  asm volatile("ld.global.nc.u32 %0, [%1];" : "=r"(v) : "l"(p));
  return v;
}
__device__ __forceinline__ uint4 ldg_nc4(const void* p) {
  uint4 v; asm volatile("ld.global.nc.L1::no_allocate.v4.u32 {%0,%1,%2,%3}, [%4];" : "=r"(v.x), "=r"(v.y), "=r"(v.z), "=r"(v.w) : "l"(p)); return v;
}
__device__ __forceinline__ uint4 ldg_stream4(const void* p) {
  uint4 v;
  asm volatile("ld.global.nc.L1::no_allocate.L2::cache_hint.v4.u32 {%0,%1,%2,%3}, [%4], %5;" : "=r"(v.x), "=r"(v.y), "=r"(v.z), "=r"(v.w) : "l"(p), "l"(l2_stream()));
  return v;
}
__device__ __forceinline__ void stg4(void* p, uint4 v) {
  asm volatile("st.global.v4.u32 [%0], {%1,%2,%3,%4};" ::"l"(p), "r"(v.x), "r"(v.y), "r"(v.z), "r"(v.w) : "memory");
}
__device__ __forceinline__ void wait_counter(const uint32_t* p, uint32_t target) {
  uint32_t n = 0;
  while (__any_sync(0xffffffffu, (int)(ld_acquire(p) - target) < 0)) { watchdog(n); }
}
__device__ __forceinline__ uint32_t tagf(float v, uint32_t tag) { return (__float_as_uint(v) & ~3u) | tag; }
__device__ __forceinline__ bool tag_ok(uint4 v, uint32_t tag) { return (((v.x ^ tag) | (v.y ^ tag) | (v.z ^ tag) | (v.w ^ tag)) & 3u) == 0; }
__device__ __forceinline__ float untag_sum(uint32_t a, uint32_t b) { return __uint_as_float(a & ~3u) + __uint_as_float(b & ~3u); }
__device__ __forceinline__ uint4 poll4(const uint32_t* p, uint32_t tag) {
  uint4 v = ld_relaxed4(p);
  uint32_t n = 0;
  while (!__all_sync(0xffffffffu, tag_ok(v, tag))) { v = ld_relaxed4(p); watchdog(n); }
  return v;
}
__device__ __forceinline__ float bf_lo(uint32_t v) { return __uint_as_float(v << 16); }
__device__ __forceinline__ float bf_hi(uint32_t v) { return __uint_as_float(v & 0xffff0000u); }
__device__ __forceinline__ uint32_t pack_bf(float lo, float hi) {
  uint32_t r; asm("cvt.rn.bf16x2.f32 %0, %1, %2;" : "=r"(r) : "f"(hi), "f"(lo)); return r;
}
__device__ __forceinline__ float rbf(float v) { return __uint_as_float(pack_bf(0.f, v) & 0xffff0000u); }
__device__ __forceinline__ uint32_t hmul2(uint32_t a, uint32_t b) {
  uint32_t r; asm("mul.rn.bf16x2 %0, %1, %2;" : "=r"(r) : "r"(a), "r"(b)); return r;
}
__device__ __forceinline__ uint32_t hadd2(uint32_t a, uint32_t b) {
  uint32_t r; asm("add.rn.bf16x2 %0, %1, %2;" : "=r"(r) : "r"(a), "r"(b)); return r;
}
__device__ __forceinline__ uint32_t hsub2(uint32_t a, uint32_t b) {
  uint32_t r; asm("sub.rn.bf16x2 %0, %1, %2;" : "=r"(r) : "r"(a), "r"(b)); return r;
}
__device__ __forceinline__ uint32_t hmax2(uint32_t a, uint32_t b) {
  uint32_t r; asm("max.bf16x2 %0, %1, %2;" : "=r"(r) : "r"(a), "r"(b)); return r;
}
__device__ __forceinline__ float rcp(float x) { float r; asm("rcp.approx.ftz.f32 %0, %1;" : "=f"(r) : "f"(x)); return r; }
__device__ __forceinline__ float ex2(float x) { float r; asm("ex2.approx.ftz.f32 %0, %1;" : "=f"(r) : "f"(x)); return r; }
__device__ __forceinline__ void stmatrix4(uint32_t addr, uint32_t a, uint32_t b, uint32_t c, uint32_t d) {
  asm volatile("stmatrix.sync.aligned.m8n8.x4.shared.b16 [%0], {%1,%2,%3,%4};" ::"r"(addr), "r"(a), "r"(b), "r"(c), "r"(d) : "memory");
}
__device__ __forceinline__ void ldmatrix4(uint32_t addr, uint32_t& a, uint32_t& b, uint32_t& c, uint32_t& d) {
  asm volatile("ldmatrix.sync.aligned.m8n8.x4.shared.b16 {%0,%1,%2,%3}, [%4];" : "=r"(a), "=r"(b), "=r"(c), "=r"(d) : "r"(addr) : "memory");
}
__device__ __forceinline__ void ldmatrix4t(uint32_t addr, uint32_t& a, uint32_t& b, uint32_t& c, uint32_t& d) {
  asm volatile("ldmatrix.sync.aligned.m8n8.x4.trans.shared.b16 {%0,%1,%2,%3}, [%4];" : "=r"(a), "=r"(b), "=r"(c), "=r"(d) : "r"(addr) : "memory");
}
__device__ __forceinline__ void mma16816(float (&d)[4], uint32_t a0, uint32_t a1, uint32_t a2, uint32_t a3, uint32_t b0, uint32_t b1) {
  asm volatile("mma.sync.aligned.m16n8k16.row.col.f32.bf16.bf16.f32 {%0,%1,%2,%3}, {%4,%5,%6,%7}, {%8,%9}, {%0,%1,%2,%3};"
               : "+f"(d[0]), "+f"(d[1]), "+f"(d[2]), "+f"(d[3]) : "r"(a0), "r"(a1), "r"(a2), "r"(a3), "r"(b0), "r"(b1));
}
__device__ __forceinline__ void sts1(uint32_t a, uint32_t v) { asm volatile("st.shared.u32 [%0], %1;" ::"r"(a), "r"(v) : "memory"); }
__device__ __forceinline__ uint4 lds4(uint32_t a) {
  uint4 v; asm volatile("ld.shared.v4.u32 {%0,%1,%2,%3}, [%4];" : "=r"(v.x), "=r"(v.y), "=r"(v.z), "=r"(v.w) : "r"(a) : "memory"); return v;
}
__device__ __forceinline__ uint2 lds2(uint32_t a) {
  uint2 v; asm volatile("ld.shared.v2.u32 {%0,%1}, [%2];" : "=r"(v.x), "=r"(v.y) : "r"(a) : "memory"); return v;
}
__device__ __forceinline__ uint32_t lds1(uint32_t a) {
  uint32_t v; asm volatile("ld.shared.u32 %0, [%1];" : "=r"(v) : "r"(a) : "memory"); return v;
}
__device__ __forceinline__ void sts2(uint32_t a, uint32_t x, uint32_t y) { asm volatile("st.shared.v2.u32 [%0], {%1,%2};" ::"r"(a), "r"(x), "r"(y) : "memory"); }
__device__ __forceinline__ void sts4(uint32_t a, uint4 v) {
  asm volatile("st.shared.v4.u32 [%0], {%1,%2,%3,%4};" ::"r"(a), "r"(v.x), "r"(v.y), "r"(v.z), "r"(v.w) : "memory");
}
__device__ __forceinline__ float silu_f(float v) { return __fdividef(v, 1.f + __expf(-v)); }
__device__ __forceinline__ uint32_t hfma2(uint32_t a, uint32_t b, uint32_t c) {
  uint32_t r; asm("fma.rn.bf16x2 %0, %1, %2, %3;" : "=r"(r) : "r"(a), "r"(b), "r"(c)); return r;
}
__device__ __forceinline__ void split_inv(float sd, uint32_t& ih, uint32_t& il) {
  const float inv = rcp(sd);
  ih = pack_bf(inv, inv);
  const float lo = inv - bf_lo(ih);
  il = pack_bf(lo, lo);
}
__device__ __forceinline__ uint32_t ln_norm(uint32_t x, uint32_t mean2, uint32_t ih, uint32_t il) {
  const uint32_t d = hsub2(x, mean2);
  return hfma2(d, ih, hmul2(d, il));
}
__device__ __forceinline__ uint32_t modul(uint32_t n, uint32_t c1, uint32_t sh) { return hadd2(hmul2(n, c1), sh); }
__device__ __forceinline__ uint32_t ln_mod(uint32_t x, uint32_t mean2, uint32_t ih, uint32_t il, uint32_t c1, uint32_t sh) {
  return modul(ln_norm(x, mean2, ih, il), c1, sh);
}

#define R8(a, i) "+f"(a[i]), "+f"(a[i + 1]), "+f"(a[i + 2]), "+f"(a[i + 3]), "+f"(a[i + 4]), "+f"(a[i + 5]), "+f"(a[i + 6]), "+f"(a[i + 7])
#define D64 "{%0,%1,%2,%3,%4,%5,%6,%7,%8,%9,%10,%11,%12,%13,%14,%15,%16,%17,%18,%19,%20,%21,%22,%23,%24,%25,%26,%27,%28,%29,%30,%31," \
            "%32,%33,%34,%35,%36,%37,%38,%39,%40,%41,%42,%43,%44,%45,%46,%47,%48,%49,%50,%51,%52,%53,%54,%55,%56,%57,%58,%59,%60,%61,%62,%63}"
template <int TB>
__device__ __forceinline__ void mma_ss(float (&d)[64], uint64_t da, uint64_t db, int sc) {
  asm volatile("{\n.reg .pred p;\nsetp.ne.b32 p, %66, 0;\n"
               "wgmma.mma_async.sync.aligned.m64n128k16.f32.bf16.bf16 " D64 ", %64, %65, p, 1, 1, 0, %67;\n}"
               : R8(d, 0), R8(d, 8), R8(d, 16), R8(d, 24), R8(d, 32), R8(d, 40), R8(d, 48), R8(d, 56)
               : "l"(da), "l"(db), "r"(sc), "n"(TB));
}
template <int TB>
__device__ __forceinline__ void mma_rs(float (&d)[64], uint32_t a0, uint32_t a1, uint32_t a2, uint32_t a3, uint64_t db, int sc) {
  asm volatile("{\n.reg .pred p;\nsetp.ne.b32 p, %69, 0;\n"
               "wgmma.mma_async.sync.aligned.m64n128k16.f32.bf16.bf16 " D64 ", {%64,%65,%66,%67}, %68, p, 1, 1, %70;\n}"
               : R8(d, 0), R8(d, 8), R8(d, 16), R8(d, 24), R8(d, 32), R8(d, 40), R8(d, 48), R8(d, 56)
               : "r"(a0), "r"(a1), "r"(a2), "r"(a3), "l"(db), "r"(sc), "n"(TB));
}
#define D128 "{%0,%1,%2,%3,%4,%5,%6,%7,%8,%9,%10,%11,%12,%13,%14,%15,%16,%17,%18,%19,%20,%21,%22,%23,%24,%25,%26,%27,%28,%29,%30,%31," \
             "%32,%33,%34,%35,%36,%37,%38,%39,%40,%41,%42,%43,%44,%45,%46,%47,%48,%49,%50,%51,%52,%53,%54,%55,%56,%57,%58,%59,%60,%61,%62,%63," \
             "%64,%65,%66,%67,%68,%69,%70,%71,%72,%73,%74,%75,%76,%77,%78,%79,%80,%81,%82,%83,%84,%85,%86,%87,%88,%89,%90,%91,%92,%93,%94,%95," \
             "%96,%97,%98,%99,%100,%101,%102,%103,%104,%105,%106,%107,%108,%109,%110,%111,%112,%113,%114,%115,%116,%117,%118,%119,%120,%121,%122,%123,%124,%125,%126,%127}"
#define R128(d, e) R8(d, 0), R8(d, 8), R8(d, 16), R8(d, 24), R8(d, 32), R8(d, 40), R8(d, 48), R8(d, 56), \
                   R8(e, 0), R8(e, 8), R8(e, 16), R8(e, 24), R8(e, 32), R8(e, 40), R8(e, 48), R8(e, 56)
__device__ __forceinline__ void mma256_ss(float (&d)[64], float (&e)[64], uint64_t da, uint64_t db, int sc) {
  asm volatile("{\n.reg .pred p;\nsetp.ne.b32 p, %130, 0;\n"
               "wgmma.mma_async.sync.aligned.m64n256k16.f32.bf16.bf16 " D128 ", %128, %129, p, 1, 1, 0, 1;\n}"
               : R128(d, e) : "l"(da), "l"(db), "r"(sc));
}
__device__ __forceinline__ void mma256_rs(float (&d)[64], float (&e)[64], uint32_t a0, uint32_t a1, uint32_t a2, uint32_t a3, uint64_t db) {
  asm volatile("{\n.reg .pred p;\nsetp.ne.b32 p, 1, 0;\n"
               "wgmma.mma_async.sync.aligned.m64n256k16.f32.bf16.bf16 " D128 ", {%128,%129,%130,%131}, %132, p, 1, 1, 1;\n}"
               : R128(d, e) : "r"(a0), "r"(a1), "r"(a2), "r"(a3), "l"(db));
}
template <int N> __device__ __forceinline__ void keep(float (&a)[N]) {
#pragma unroll
  for (int i = 0; i < N; i++) asm volatile("" : "+f"(a[i])::"memory");
}
template <int N> __device__ __forceinline__ void keep(uint32_t (&a)[N]) {
#pragma unroll
  for (int i = 0; i < N; i++) asm volatile("" : "+r"(a[i])::"memory");
}

#define STAMP(idx) do {} while (0)
#define PROF(grp, cond, idx) do {} while (0)

constexpr float SCL2 = 1.4426950408889634f * 0.08838834764831845f;

__device__ __forceinline__ void pack_p(const float (&s)[64], uint32_t (&p)[32]) {
#pragma unroll
  for (int i = 0; i < 32; i++) p[i] = pack_bf(s[2 * i], s[2 * i + 1]);
}

__device__ __forceinline__ void issue_qk(float (&s)[64], uint32_t q0, uint32_t q1, uint32_t kslot) {
  const uint64_t db = make_desc(kslot, 16, 1024), da0 = make_desc(q0, 16, 1024), da1 = make_desc(q1, 16, 1024);
#pragma unroll
  for (int kk = 0; kk < 8; kk++) mma_ss<0>(s, (kk < 4 ? da0 : da1) + (kk & 3) * 2, db + (kk >> 2) * 1024 + (kk & 3) * 2, kk != 0);
}
__device__ __forceinline__ void issue_pv(float (&o)[64], uint32_t (&p)[32], uint32_t vslot, int acc) {
  uint64_t db = make_desc(vslot, 16384, 1024);
#pragma unroll
  for (int kk = 0; kk < 8; kk++)
    mma_rs<1>(o, p[4 * kk], p[4 * kk + 1], p[4 * kk + 2], p[4 * kk + 3], db + kk * 128, kk == 0 ? acc : 1);
}

template <int H>
__device__ __forceinline__ void store_chunk(const float (&a)[64], uint32_t addr) {
#pragma unroll
  for (int i = 8 * H; i < 8 * H + 8; i += 2)
    stmatrix4(addr ^ ((i & 7) << 4), pack_bf(a[4 * i], a[4 * i + 1]), pack_bf(a[4 * i + 2], a[4 * i + 3]),
              pack_bf(a[4 * i + 4], a[4 * i + 5]), pack_bf(a[4 * i + 6], a[4 * i + 7]));
}
template <int H>
__device__ __forceinline__ void store_chunk(const float (&a)[64], float i0, float i1, uint32_t addr) {
#pragma unroll
  for (int i = 8 * H; i < 8 * H + 8; i += 2)
    stmatrix4(addr ^ ((i & 7) << 4), pack_bf(a[4 * i] * i0, a[4 * i + 1] * i0), pack_bf(a[4 * i + 2] * i1, a[4 * i + 3] * i1),
              pack_bf(a[4 * i + 4] * i0, a[4 * i + 5] * i0), pack_bf(a[4 * i + 6] * i1, a[4 * i + 7] * i1));
}
__device__ __forceinline__ float inv_quad_sum(float l) {
  l += __shfl_xor_sync(0xffffffffu, l, 1);
  l += __shfl_xor_sync(0xffffffffu, l, 2);
  return rcp(l);
}

__device__ __forceinline__ void write_table(uint32_t table, bool ca, uint32_t t, const uint4& m0, const uint4& m1) {
  float c0 = untag_sum(m0.x, m1.x), c1 = untag_sum(m0.y, m1.y), c2 = untag_sum(m0.z, m1.z), c3 = untag_sum(m0.w, m1.w);
  if (ca) { c0 = 1.f + rbf(c0); c1 = 1.f + rbf(c1); c2 = 1.f + rbf(c2); c3 = 1.f + rbf(c3); }
  const uint32_t d = table + (t >> 2) * 64 + (t & 1) * 32 + (t & 2) * 2 + (ca ? 0 : 8);
  sts1(d, pack_bf(c0, c1));
  sts1(d + 16, pack_bf(c2, c3));
}

__device__ __forceinline__ void ln_scalars(float mean, float var, float& mb, float& sd) {
  mb = rbf(mean);
  float r; asm("sqrt.approx.ftz.f32 %0, %1;" : "=f"(r) : "f"(rbf(rbf(var) + 1e-5f)));
  sd = rbf(r);
}

__global__ void __cluster_dims__(2, 1, 1) __launch_bounds__(384, 1) fused_kernel(const __grid_constant__ Maps maps, const Ptrs P) {
  extern __shared__ __align__(1024) uint8_t smem_raw[];
  const uint32_t base = smem_u32(smem_raw);
  const int tid = threadIdx.x, lane = tid & 31;
  const int warp = __shfl_sync(0xffffffffu, tid >> 5, 0);
  const int b = blockIdx.x;
  PROF(31, tid == 0, 0);

  if (b >= NMAIN) {
    float* sc = reinterpret_cast<float*>(smem_raw);
    float* red = sc + DM;
    for (int k = tid; k < DM; k += 384) sc[k] = rbf(silu_f(__bfloat162float(P.c[k])));
    __syncthreads();
    if (tid < 256) {
      const int col = 2048 + (b - NMAIN) * 1024 + (tid & 127) * 8, r0 = (tid >> 7) * 512;
      float acc[8];
#pragma unroll
      for (int e = 0; e < 8; e++) acc[e] = 0.f;
#pragma unroll 1
      for (int r = r0; r < r0 + 512; r += HU) {
        uint4 w[HU];
#pragma unroll
        for (int u = 0; u < HU; u++) w[u] = ldg_stream4(P.w_mod + (size_t)(r + u) * NMOD + col);
#pragma unroll
        for (int u = 0; u < HU; u++) {
          float s = sc[r + u];
          acc[0] += s * bf_lo(w[u].x); acc[1] += s * bf_hi(w[u].x); acc[2] += s * bf_lo(w[u].y); acc[3] += s * bf_hi(w[u].y);
          acc[4] += s * bf_lo(w[u].z); acc[5] += s * bf_hi(w[u].z); acc[6] += s * bf_lo(w[u].w); acc[7] += s * bf_hi(w[u].w);
        }
      }
      if (tid >= 128) {
#pragma unroll
        for (int e = 0; e < 8; e++) red[(tid & 127) * 8 + e] = acc[e];
      }
      const uint32_t tag = ld_relaxed(&g_epoch) % 3 + 1;
      bar_sync(1, 256);
      if (tid < 128) {
        uint32_t o[8];
#pragma unroll
        for (int e = 0; e < 8; e++) o[e] = __float_as_uint(rbf(acc[e] + red[tid * 8 + e])) | tag;
        st_relaxed4(g_mod + col, o[0], o[1], o[2], o[3]);
        st_relaxed4(g_mod + col + 4, o[4], o[5], o[6], o[7]);
        const uint4 wr = ldg_nc4(P.w_r + tid * 8);
        const uint32_t wv[4] = {wr.x, wr.y, wr.z, wr.w};
        float dsum = 0.f;
#pragma unroll
        for (int e = 0; e < 8; e++) {
          const float m = bf_hi(o[e]);
          dsum += (b == NMAIN + 2 ? rbf(1.f + m) : m) * ((e & 1) ? bf_hi(wv[e >> 1]) : bf_lo(wv[e >> 1]));
        }
#pragma unroll
        for (int k = 16; k > 0; k >>= 1) dsum += __shfl_xor_sync(0xffffffffu, dsum, k);
        if (lane == 0) st_relaxed(g_mod + (b - NMAIN) * 4 + warp, tagf(dsum, tag));
      }
    }
    PROF(2, tid == 0, 1);
    return;
  }

  const int rank = b & 1;
  const int rb = ((b >> 4) << 1) | rank, cj = (b >> 1) & 7;
  const bool late = b & 4;
  const uint32_t bfull = base + OFF_BAR, bempty = bfull + NSLOT * 8;
  const uint32_t gfull = bempty + NSLOT * 8, gempty = gfull + 32;
  const uint32_t bar_ofull = gempty + 32;
  const uint32_t bar_ofree = bar_ofull + 32;
  const uint32_t bar_par = bar_ofree + 32;
  const uint32_t bar_mod = bar_par + 8;
  const uint32_t bar_pread = bar_mod + 8;
  const uint32_t bar_xres = bar_pread + 8;
  const uint32_t bar_ring = bar_xres + 8;
  const uint32_t bar_box = bar_ring + 24;
  const uint32_t bar_go = bar_box + 96;
  const uint32_t bar_go2 = bar_go + 16;
  const uint32_t bar_cnt = bar_go + 24;
  const uint32_t xfull = bar_go + 40, xempty = xfull + 32;
  const uint32_t bar_hw = xempty + 32, bar_hx = bar_hw + 8;
  const uint32_t bar_hpub = bar_hx + 16;
  const uint32_t bar_win = bar_hpub + 16;
  const uint32_t bar_rx = bar_win + 8;
  const uint32_t bar_sel = bar_rx + 8;
  const uint32_t bar_gate = bar_sel + 8;
  const uint32_t bar_rel = bar_gate + 8;
  const uint32_t bar_od = bar_rel + 8;
  const uint32_t bar_mod2 = bar_od + 8;
  const uint32_t bar_res = bar_go + 8;
  const uint32_t stage = base + OFF_STAGE, par = base + OFF_PAR;

  if (warp == 10 && elect_one()) prefetch_map(&maps.wm);
  if (warp == 8 && elect_one()) {
    for (int s = 0; s < NSLOT; s++) { mbar_init(bfull + s * 8, 1); mbar_init(bempty + s * 8, 16); }
    for (int s = 0; s < 4; s++) { mbar_init(gfull + s * 8, 1); mbar_init(gempty + s * 8, 16); mbar_init(xfull + s * 8, 1); mbar_init(xempty + s * 8, 8); mbar_init(bar_ofree + s * 8, 1); mbar_init(bar_ofull + s * 8, 128); }
    mbar_init(bar_par, 64); mbar_init(bar_mod, 256); mbar_init(bar_pread, 2); mbar_init(bar_xres, 1);
    mbar_init(bar_ring, 8); mbar_init(bar_ring + 8, 8); mbar_init(bar_ring + 16, 8);
    mbar_init(bar_go, 1); mbar_init(bar_go2, 1); mbar_init(bar_cnt, 1); mbar_init(bar_cnt + 8, 1); mbar_init(bar_hpub, 8); mbar_init(bar_hpub + 8, 8); mbar_init(bar_res, 1); mbar_init(bar_win, 1); mbar_init(bar_rx, 1); mbar_init(bar_sel, 64); mbar_init(bar_gate, 8); mbar_init(bar_rel, 8); mbar_init(bar_od, 1); mbar_init(bar_mod2, 64);
    for (int s = 0; s < 12; s++) mbar_init(bar_box + s * 8, 1);
    asm volatile("fence.mbarrier_init.release.cluster;" ::: "memory");
    prefetch_map(&maps.x); prefetch_map(&maps.wq); prefetch_map(&maps.k); prefetch_map(&maps.v);
  }
  if (warp == 9 && elect_one()) {
    mbar_init(bar_hw, 1); mbar_init(bar_hx, 1); mbar_init(bar_hx + 8, 1);
    asm volatile("fence.mbarrier_init.release.cluster;" ::: "memory");
    mbar_expect_tx(bar_hw, 32768);
    mbar_expect_tx(bar_hx, 16384);
    mbar_expect_tx(bar_hx + 8, 16384);
    const __nv_bfloat16* xs = P.x + (size_t)(rb * 128 + cj * 16) * DM;
    bulk_load(base + 2 * GST_BYTES, xs, 16384, bar_hx);
    if (!late) {
      tma2d(stage, &maps.wm, (b >> 1) * 32, rank * 512, bar_hw);
      tma2d(stage + 16384, &maps.wm, (b >> 1) * 32, rank * 512 + 256, bar_hw);
    }
    bulk_load(base + 3 * GST_BYTES, xs + 8 * DM, 16384, bar_hx + 8);
  }
  cluster_arrive();

  if (warp >= 8) {
    asm volatile("setmaxnreg.dec.sync.aligned.u32 40;");
    if (warp < 10) bar_arrive(1, 320);
    const uint32_t epoch = ld_relaxed(&g_epoch);
    cluster_wait();
    if (warp == 8) {
      const int kvrow = (cj >> 1) * SK + (SK - WIN);
      int wch = cj * 8 + rank * 2;
#pragma unroll 1
      for (int ps = 0; ps < 3; ps++) {
        const CUtensorMap* mw = ps == 2 ? &maps.wo : &maps.wq;
        const uint32_t xt = ps == 1 ? XT1 : XT2, wt = ps == 0 ? WT0 : (ps == 1 ? WT1 : WT2);
        const int nst = ps == 2 ? 32 : 16;
#pragma unroll 1
        for (int i = 0; i < nst; i++) {
          const uint32_t bf = gfull + (i & 3) * 8;
          const int kt = ps == 2 ? otile_of(i, cj) : (ps ? i : slice_of(i) + (b & 14)) & 15;
          const uint32_t wd = base + unit_of(wt, i & 3) + rank * UNIT, xd = base + unit_of(xt, i & 3);
          const uint8_t* xs = g_act + (uint32_t)(rb * 80 + (ps - 1) * 16 + kt) * UNIT;
          if (ps == 0 && i == HD) mbar_wait(bar_mod, 0);
          const bool xfirst = ps && i < 2;
          const bool own = ps == 2 && i >= 2 && i < 6;
          if (ps == 2 && i == 0) mbar_wait(bar_ofree + 24, 0);
          if (i == 0) fence_async();
          mbar_wait(gempty + (i & 3) * 8, ((i >> 2) & 1) ^ 1);
          if (elect_one()) {
            mbar_expect_tx(bf, ps && !own ? GST_BYTES : 2 * UNIT);
            if (xfirst) bulk_load_stream(xd, xs, UNIT, bf);
          }
          if (ps && i < 4) mbar_wait(bempty + i * 8, 1);
          if (elect_one()) tma3d_mc<true>(wd, mw, 0, (i == 31 ? kt ^ (rank * 8) : kt) * 64, i == 31 ? cj * 2 : wch, bf);
          if (ps) {
            if (i == 20 || i == 26) { mbar_wait(bar_cnt + (i & 2) * 4, 0); fence_async(); }
            if (i == RES0) mbar_wait(bar_res, 0);
            if (i == 4 * ps - 2) mbar_wait(bar_ofree + (ps - 1) * 16, 0);
            if (elect_one()) {
              if (i == 31) bulk_load(xd, xs, UNIT, bf); else if (!xfirst && !own) bulk_load_stream(xd, xs, UNIT, bf);
              mbar_arrive_pred(bar_go, i == GOST - 1);
              if (PG0 < 16) mbar_arrive_pred(bar_go2, ps == 1 && i == PG0);
              mbar_arrive_pred(bar_od, i == (ps == 1 ? ODS1 : ODS));
              if (i == RES0) mbar_expect_tx(bar_xres, 32768);
              if (i == RES0 || i == RES1) tma2d(base + OFF_RES + (i == RES1) * UNIT, &maps.x, cj * 128 + (i == RES1) * 64, rb * 128, bar_xres);
            }
          }
        }
        if (ps == 2) break;
        wch = ps ? ((wch >> 3) ^ rank) * 2 : wch + 4;
#pragma unroll 1
        for (int u = 0; u < 16; u++) {
          const bool isk = (u == 0) || ((u & 1) && u < 15);
          const int blk = (isk ? (u + 1) >> 1 : (u == 15 ? 7 : (u >> 1) - 1)) & 3;
          const uint32_t sl = base + unit_of(ps ? AT1 : AT0, u & 3) + rank * UNIT, bf = bfull + (u & 3) * 8;
          if (u < 4) mbar_wait(gempty + ((u + 1) >> 1) * 8, 1);
          mbar_wait(bempty + (u & 3) * 8, ((u >> 2) & 1) ^ 1);
          if (elect_one()) {
            mbar_arrive_pred(bar_go2, ps && u + 16 == PG0);
            mbar_expect_tx(bf, SLOT_BYTES);
            tma3d_mc<false>(sl, isk ? &maps.k : &maps.v, 0, kvrow + blk * 128, rank, bf);
          }
        }
      }
      if (elect_one()) mbar_expect_tx(bar_rx, UNIT);
      mbar_wait(bar_rel, 0);
      if (elect_one()) {
        bulk_load_stream(base + UNIT, g_act + (uint32_t)(rb * 80 + 16 + otile_of(31, cj ^ 1)) * UNIT, UNIT, bar_rx);
      }
      if (b < NFFN) {
#pragma unroll 1
        for (int u = 0; u < 12; u++) {
          const uint32_t dst = base + unit_of(u < 4 ? FT_G : (u < 8 ? FT_U : FT_D), u & 3);
          if (elect_one()) mbar_expect_tx(bar_box + u * 8, UNIT);
          if (u == FB0 || u == FB1 || u == FB2) mbar_wait(bar_ring + (u == FB2 ? 16 : u == FB1 ? 8 : 0), 0);
          const int fp = u < FPB ? FPACE0 : FPACE;
          if (u >= fp) mbar_wait(bar_box + (u - fp) * 8, 0);
          if (elect_one()) {
            if (u < 8) tma2d(dst, u < 4 ? &maps.wg : &maps.wu, b * 32, (u & 3) * 256, bar_box + u * 8);
            else tma3d(dst, &maps.wd, 0, b * 32, (u - 8) * 4, bar_box + u * 8);
          }
        }
      }
    } else if (warp == 9) {
      const uint32_t target = 8 * (epoch + 1);
      uint32_t hmask = 0;
#pragma unroll 1
      for (int i = 0; i < 16; i++) {
        if (i == HDX) mbar_wait(bar_mod, 0);
        const int kt = (2 * cj + slice_of(i)) & 15;
        const uint32_t need = i == 15 ? 0xffffu : 1u << kt;
        if (i >= NRS && (hmask & need) != need) {
          uint32_t n = 0;
          do { hmask = __ballot_sync(0xffffffffu, ld_acquire(&g_cnt_h[rb * 32 + (lane & 15)]) == epoch + 1); watchdog(n); } while ((hmask & need) != need);
          PROF(1, lane == 0 && i == NRS, 26);
          fence_async();
        }
        mbar_wait(xempty + (i & 3) * 8, ((i >> 2) & 1) ^ 1);
        if (elect_one()) {
          mbar_expect_tx(xfull + (i & 3) * 8, UNIT);
          if (i < NRS) tma2d(base + (i & 3) * GST_BYTES, &maps.x, kt * 64, rb * 128, xfull + (i & 3) * 8);
          else bulk_load_stream(base + (i & 3) * GST_BYTES, g_act + (uint32_t)(rb * 80 + kt) * UNIT, UNIT, xfull + (i & 3) * 8);
        }
      }
      prefetch_map(&maps.wo);
#pragma unroll 1
      for (int t = 0; t < 4; t++) {
        if (t & 1) mbar_wait(bar_od, t >> 1);
#pragma unroll 1
        for (int p = 0; p < 32768 / OPS; p++) {
          const uint32_t w = p / (16384 / OPS), c = (p / (8192 / OPS)) & 1, off = w * 8192 + (p % (8192 / OPS)) * OPS;
          mbar_wait(bar_ofull + (t & 1) * 16 + w * 8, t >> 1);
          if (elect_one()) {
            bulk_store(g_act + (uint32_t)(rb * 80 + 16 + (cj * 4 + t) * 2 + c) * UNIT + off, base + unit_of(QT, 2 * t + c) + off, OPS);
            asm volatile("cp.async.bulk.commit_group;" ::: "memory");
            asm volatile("cp.async.bulk.wait_group.read %0;" ::"n"(OFL) : "memory");
          }
        }
        if (elect_one()) {
          asm volatile("cp.async.bulk.wait_group.read 0;" ::: "memory");
          mbar_arrive(t < 3 ? bar_ofree + t * 8 : bar_res);
          asm volatile("cp.async.bulk.wait_group 0;" ::: "memory");
          fence_async();
          red_release(&g_cnt_o[((rb * 4 + t) * 2 + (cj & 1)) * 32], 2);
        }
        if (t) {
          wait_counter(&g_cnt_o[(rb * 8 + 2 * t + (cj & 1)) * 32], target);
          if (t & 1) wait_counter(&g_cnt_o[(rb * 8 + (t == 1 ? cj & 1 : 7 - (cj & 1))) * 32], target);
          if (elect_one()) mbar_arrive(t == 1 ? bar_ofree + 24 : bar_cnt + t * 8 - 16);
        }
      }
      PROF(2, lane == 0, 27);
      const uint32_t tag = epoch % 3 + 1;
      const uint32_t* inbox = g_cand + (b >> 1) % CR * 512 + (lane & 15) * CS;
      mbar_wait(bar_ring + 16, 0);
      uint32_t c0 = ld_relaxed(inbox), n = 0;
#define CAND_STEP(cv)                                                                                        \
      {                                                                                                      \
        const bool valid = (cv & 3u) == tag, all = __all_sync(0xffffffffu, valid);                           \
        const uint32_t best = __reduce_max_sync(0xffffffffu, valid ? cv : 0u);                               \
        const uint32_t blk = __ffs(__ballot_sync(0xffffffffu, cv == best)) - 1;                              \
        if (best) sts2(par + PAR_CONST + 56, best, (blk << 7 | (~best >> 2 & 127)) | (all ? 0x1800 : 0x800)); \
        if (all) break;                                                                                      \
        cv = ld_relaxed(inbox);                                                                              \
      }
      while (true) { CAND_STEP(c0) watchdog(n); }
    } else {
      const int t2 = tid - 320;
      if (late && warp == 10) {
        mbar_wait(bar_hx, 0);
        if (elect_one()) {
          tma2d(stage, &maps.wm, (b >> 1) * 32, rank * 512, bar_hw);
          tma2d(stage + 16384, &maps.wm, (b >> 1) * 32, rank * 512 + 256, bar_hw);
        }
      }
      {
        const uint32_t tag = epoch % 3 + 1;
        mbar_wait(bar_hx + 8, 0);
        mbar_wait(bar_hw, 0);
        __nanosleep(late ? OSL2 : OSL);
        {
          const uint32_t t7 = (warp & 1) * 64 + (lane >> 4) * 32 + 16 + (lane & 15);
          const uint32_t* pm = g_modp + ((cj * 128 + t7 * 4) & (DM - 1));
          uint4 m0, m1, m2, m3;
          uint32_t n = 0;
          do {
            m0 = ld_relaxed4(pm); m1 = ld_relaxed4(pm + 2 * DM); m2 = ld_relaxed4(pm + DM); m3 = ld_relaxed4(pm + 3 * DM);
            watchdog(n);
          } while (!__all_sync(0xffffffffu, tag_ok(m0, tag) && tag_ok(m1, tag) && tag_ok(m2, tag) && tag_ok(m3, tag)));
          write_table(par, false, t7, m0, m1);
          write_table(par, true, t7, m2, m3);
          mbar_arrive(bar_mod2);
        }
      }
      mbar_wait(bar_hpub + (warp & 1) * 8, 0);
      PROF(1, t2 == 0, 24);
#pragma unroll 1
      for (int c = 0; c < 8; c++) {
        const uint32_t off = (warp & 1) * UNIT + c * 2048 + lane * 16;
        uint8_t* dst = g_act + (uint32_t)(rb * 80 + cj * 2) * UNIT + off;
        const uint4 v0 = lds4(stage + off), v1 = lds4(stage + off + 512), v2 = lds4(stage + off + 1024), v3 = lds4(stage + off + 1536);
        stg4(dst, v0); stg4(dst + 512, v1); stg4(dst + 1024, v2); stg4(dst + 1536, v3);
      }
      __syncwarp();
      PROF(1, t2 == 0, 15);
      if (lane == 0) {
        mbar_arrive(bar_pread);
        red_release(&g_cnt_h[rb * 32 + cj * 2 + (warp & 1)], 1);
        PROF(1, t2 == 0, 25);
        prefetch_map(&maps.wg); prefetch_map(&maps.wu); prefetch_map(&maps.wd); prefetch_map(&maps.out);
      }
      __syncwarp();
      if (b < NFFN) {
        mbar_wait(bar_go2, 0);
        const __nv_bfloat16* pg = ((b & 1) ? P.w_up : P.w_gate) + (b >> 1) * 64 + (size_t)t2 * FF;
        const __nv_bfloat16* pd = P.w_down + (size_t)b * 32768 + t2 * 64;
        PROF(2, t2 == 0, 13);
#pragma unroll 1
        for (int i = 0; i < WN; i += WB) {
          uint32_t v[WB];
#pragma unroll
          for (int u = 0; u < WB; u++) {
            const int k = i + u;
            asm volatile("ld.global.cg.L2::128B.u32 %0, [%1];" : "=r"(v[u]) : "l"(k < 16 ? pg + (size_t)k * 64 * FF : pd + (k - 16) * 4096));
          }
#pragma unroll
          for (int u = 1; u < WB; u++) v[0] ^= v[u];
          sts1(par + PAR_SINK + t2 * 4, v[0]);
        }
        PROF(2, t2 == 0, 14);
      }
      const uint32_t tag = epoch % 3 + 1;
      mbar_wait(bar_go, 0);
      bar_sync(4, 64);
      if (warp == 10) {
        const uint32_t* src = g_mod + 2 * DM + cj * 128 + lane * 4;
        const uint2 wr = *reinterpret_cast<const uint2*>(P.w_r + cj * 128 + lane * 4);
        uint4 vga, vsb, vcb, vgb;
        uint32_t n = 0;
        do {
          vga = ld_relaxed4(src); vsb = ld_relaxed4(src + DM); vcb = ld_relaxed4(src + 2 * DM); vgb = ld_relaxed4(src + 3 * DM);
          watchdog(n);
        } while (!__all_sync(0xffffffffu, tag_ok(vga, tag) && tag_ok(vsb, tag) && tag_ok(vcb, tag) && tag_ok(vgb, tag)));
        const float c0 = rbf(1.f + bf_hi(vcb.x)), c1 = rbf(1.f + bf_hi(vcb.y)), c2 = rbf(1.f + bf_hi(vcb.z)), c3 = rbf(1.f + bf_hi(vcb.w));
        const float a0 = c0 * bf_lo(wr.x), a1 = c1 * bf_hi(wr.x), a2 = c2 * bf_lo(wr.y), a3 = c3 * bf_hi(wr.y);
        const uint32_t h0 = pack_bf(a0, a1), h1 = pack_bf(a2, a3);
        const uint32_t t1 = par + PAR_T1 + (lane >> 2) * 64 + (lane & 1) * 32 + (lane & 2) * 2;
        sts1(t1, h0); sts1(t1 + 8, pack_bf(a0 - bf_lo(h0), a1 - bf_hi(h0)));
        sts1(t1 + 16, h1); sts1(t1 + 24, pack_bf(a2 - bf_lo(h1), a3 - bf_hi(h1)));
        const uint32_t tg = par + PAR_SINK + (lane >> 3) * 64 + (lane & 1) * 32 + (lane & 6) * 2;
        sts1(tg, __byte_perm(vga.x, vga.y, 0x7632)); sts1(tg + 16, __byte_perm(vga.z, vga.w, 0x7632));
        sts4(par + PAR_T2 + lane * 32, make_uint4(pack_bf(c0, c1), __byte_perm(vsb.x, vsb.y, 0x7632), __byte_perm(vgb.x, vgb.y, 0x7632), __byte_perm(vga.x, vga.y, 0x7632)));
        sts4(par + PAR_T2 + lane * 32 + 16, make_uint4(pack_bf(c2, c3), __byte_perm(vsb.z, vsb.w, 0x7632), __byte_perm(vgb.z, vgb.w, 0x7632), __byte_perm(vga.z, vga.w, 0x7632)));
      } else {
        const uint4 g = poll4((lane & 8) ? g_mod + 8 - (lane & 1) * 4 : g_mod + 5 * DM + (b >> 4) * 128 + (lane & 7) * 16 + (b & 12), tag);
        sts1(par + PAR_CONST + 60, 0);
        if (lane < 8) sts1(par + PAR_CONST + 16 + lane * 4, (b & 2) ? ((b & 1) ? g.w : g.z) : ((b & 1) ? g.y : g.x));
        else if (lane < 10) sts2(par + PAR_CONST + (lane - 8) * 8, __float_as_uint(untag_sum(g.x, g.y) + untag_sum(g.z, g.w)), epoch);
      }
      __syncwarp();
#pragma unroll 4
      for (int q = 0; q < 32; q++) st_b128(g_xch + ((size_t)b * 8 * 256 + q * 64 + t2) * 4, (epoch & 1) << 16, 0, 0, 0);
      for (int q = 0; q < 2; q++) st_relaxed4(g_stats + ((size_t)cj * SEQ + rb * 128 + q * 64 + t2) * 4, 0, 0, 0, 0);
      if (b < NFFN)
        for (int q = 0; q < 2; q++) st_relaxed4(ypart_slot(b, q * 64 + t2), 0, 0, 0, 0);
      st_relaxed4(g_row + rb * 2 * DM + (t2 >> 5) * DM + cj * 128 + (t2 & 31) * 4, 0, 0, 0, 0);
      __threadfence();
      mbar_arrive(bar_par);
      mbar_wait(bar_gate, 0);
      uint32_t have = 0, n = 0;
      while (true) {
        const uint32_t st = lds1(par + PAR_CONST + 60) >> 7;
        if ((st & 31) != have) {
          const uint32_t* hsrc = g_row + (st & 15) * 2 * DM + t2 * 4;
          uint4 hv[4];
          bool ok = true;
#pragma unroll
          for (int i = 0; i < 4; i++) hv[i] = ld_pairs(hsrc + i * 256);
#pragma unroll
          for (int i = 0; i < 4; i++) {
            sts2(base + ((FT_G >> i * 4) & 15) * UNIT + (warp & 1) * 8192 + 256 + lane * 8, hv[i].x, hv[i].z);
            ok = ok && hv[i].y == tag && hv[i].w == tag;
          }
          have = __all_sync(0xffffffffu, ok) ? st & 31 : 0;
        }
        if ((st ^ have) == 32) break;
        watchdog(n);
      }
      mbar_arrive(bar_sel);
    }
    __syncwarp();
    cluster_arrive();
    {
      const uint32_t tag = epoch % 3 + 1, t3 = tid - 256;
      mbar_wait(bar_win, 0);
      uint2 win = lds2(par + PAR_CONST + 56);
      win.y &= 0x7ff;
      const uint32_t* fsrc = g_row + (win.y >> 7) * 2 * DM + (b >> 4) * 128 + (t3 & 7) * 16 + (b & 6) * 2 + ((b >> 2) & 2);
      const uint32_t* ysrc = ypart_slot(min(t3, NFFN - 1), b);
      uint2 fh = ld_pair(fsrc), fx = ld_pair(fsrc + DM);
      uint4 ya = ld_b128(ysrc);
      const float rwin = __uint_as_float(((int)win.x < 0 ? win.x & 0x7fffffffu : ~win.x) & ~0x1ffu);
      const float rs = rbf(rcp(1.f + __expf(-rbf(rwin))));
      uint32_t n = 0;
      while (__any_sync(0xffffffffu, fh.y != tag || fx.y != tag)) { fh = ld_pair(fsrc); fx = ld_pair(fsrc + DM); watchdog(n); }
      while (true) {
        const bool miss = ((ya.x & 1) | (ya.y & 1) << 1) != tag;
        if (!__any_sync(0xffffffffu, miss)) break;
        if (miss) ya = ld_b128(ysrc);
        watchdog(n);
      }
      PROF(8, t3 == 0, 5);
      float y[8] = {bf_lo(ya.x & ~1u), bf_hi(ya.x), bf_lo(ya.y & ~1u), bf_hi(ya.y), bf_lo(ya.z), bf_hi(ya.z), bf_lo(ya.w), bf_hi(ya.w)};
#pragma unroll
      for (int h = 4; h > 0; h >>= 1) {
        const bool up = lane & (h * 2);
#pragma unroll
        for (int e = 0; e < h; e++) y[e] = (up ? y[e + h] : y[e]) + __shfl_xor_sync(0xffffffffu, up ? y[e] : y[e + h], h * 2);
      }
      y[0] += __shfl_xor_sync(0xffffffffu, y[0], 1);
      if (!(lane & 1)) sts1(par + PAR_RED + 64 + t3 * 2, __float_as_uint(y[0]));
      bar_sync(4, 128);
      if (t3 < 8) {
        float y0 = 0.f;
#pragma unroll
        for (int w7 = 0; w7 < 7; w7++) y0 += __uint_as_float(lds1(par + PAR_RED + 64 + w7 * 32 + t3 * 4));
        const uint32_t gv = lds1(par + PAR_CONST + 16 + t3 * 4);
        const uint32_t upd = hmul2(pack_bf(y0, y0), pack_bf(rs, rs));
        const uint32_t r = hadd2(fx.x, hmul2(__byte_perm(gv, gv, 0x3232), hadd2(fh.x, upd)));
        reinterpret_cast<uint16_t*>(P.out)[(size_t)win.y * DM + (b >> 4) * 128 + t3 * 16 + (b & 15)] = (b & 1) ? r >> 16 : r;
        if (b == 0 && t3 == 0) st_relaxed(&g_epoch, epoch + 1);
      }
      PROF(31, t3 == 0, 36);
    }
    cluster_wait();
  } else {
    const int wg = warp >> 2;

    uint32_t tag;
    {
      uint32_t* const pmod = g_modp + rank * 2 * DM + (b >> 1) * 32 + lane;
      uint32_t* const pln = g_ln1 + (rb * 128 + cj * 16 + warp) * 4;
      uint32_t sc[8];
#pragma unroll
      for (int k = 0; k < 8; k++) sc[k] = ldg_nc1(P.c + rank * 512 + warp * 64 + k * 8 + (lane & 3) * 2);
      const uint32_t epoch = ld_relaxed(&g_epoch);
      if (warp == 0) st_relaxed(pmod, 0);
      if (lane == 0) { st_b128(pln, 0, 0, 0, 0); st_b128(pln + 32, 0, 0, 0, 0); }
      asm volatile("setmaxnreg.inc.sync.aligned.u32 232;");
      bar_sync(1, 320);
#pragma unroll
      for (int k = 0; k < 8; k++) sc[k] = pack_bf(silu_f(bf_lo(sc[k])), silu_f(bf_hi(sc[k])));
      keep(sc);
      tag = epoch % 3 + 1;
#pragma unroll
      for (int part = 0; part < 4; part++) {
        if (!(part & 1)) {
          const uint32_t xa = base + (2 + part / 2) * GST_BYTES + warp * 2048 + lane * 16;
          mbar_wait(bar_hx + part * 4, 0);
          float s0 = 0.f, s1 = 0.f, q0 = 0.f, q1 = 0.f;
#pragma unroll
          for (int q = 0; q < 4; q++) {
            const uint4 xv = lds4(xa + q * 512);
            const uint32_t u[4] = {xv.x, xv.y, xv.z, xv.w};
#pragma unroll
            for (int e = 0; e < 4; e++) { const float lo = bf_lo(u[e]), hi = bf_hi(u[e]); s0 += lo; s1 += hi; q0 += lo * lo; q1 += hi * hi; }
          }
          s0 += s1; q0 += q1;
#pragma unroll
          for (int o = 16; o > 0; o >>= 1) { s0 += __shfl_xor_sync(0xffffffffu, s0, o); q0 += __shfl_xor_sync(0xffffffffu, q0, o); }
          const float mean = s0 * (1.f / DM);
          float mb, sd;
          ln_scalars(mean, fmaxf(q0 * (1.f / DM) - mean * mean, 0.f), mb, sd);
          uint32_t ih, il;
          split_inv(sd, ih, il);
          if (lane == 0) st_b128(pln + part * 16, pack_bf(mb, mb), ih, il, tag);
          PROF(1, tid == 0 && part == 2, 4);
        } else if (late == (part == 3)) {
          const uint32_t fr = (lane & 7) + (lane >> 4) * 8, tq = lane & 3;
          const uint32_t wa = stage + warp * 4096 + fr * 64 + ((((lane >> 3) & 1) ^ ((fr >> 1) & 3)) << 4);
          float d0[4] = {0.f, 0.f, 0.f, 0.f}, d1[4] = {0.f, 0.f, 0.f, 0.f};
          mbar_wait(bar_hw, 0);
#pragma unroll
          for (int ks = 0; ks < 4; ks++) {
            uint32_t w[8];
            ldmatrix4t(wa + ks * 1024, w[0], w[1], w[2], w[3]);
            ldmatrix4t((wa ^ 32) + ks * 1024, w[4], w[5], w[6], w[7]);
            mma16816(d0, w[0], w[1], w[2], w[3], sc[2 * ks], sc[2 * ks + 1]);
            mma16816(d1, w[4], w[5], w[6], w[7], sc[2 * ks], sc[2 * ks + 1]);
          }
          sts1(base + 2 * GST_BYTES + warp * 2048 + (tq * 8 + (lane >> 2)) * 4, __float_as_uint((tq & 2) ? ((tq & 1) ? d1[2] : d1[0]) : ((tq & 1) ? d0[2] : d0[0])));
          bar_sync(1, 256);
          if (warp == 0) {
            float s = 0.f;
#pragma unroll
            for (int w8 = 0; w8 < 8; w8++) s += __uint_as_float(lds1(base + 2 * GST_BYTES + w8 * 2048 + lane * 4));
            st_relaxed(pmod, (__float_as_uint(s) & ~3u) | tag);
          }
          PROF(1, tid == 0, 3);
        }
      }
      cluster_wait();
      if (wg == 1) bar_arrive(2, 256);
    }

    float f0 = 0.f, f1 = 0.f;
    const uint32_t rempty = lane < 2 ? mapa(bempty, lane & 1) : 0;
    constexpr uint32_t GE = NSLOT * 8 + 32;
    float o[64], s[64];
#pragma unroll 1
    for (int ps = 0; ps < 3; ps++) {
      {
        const uint32_t xt = ps == 1 ? XT1 : XT2, wt = ps == 1 ? WT1 : WT2;
        const int nst = ps == 2 ? 28 : 14;
        if (ps == 0) {
          float ga[64], gb[64];
#pragma unroll
          for (int i = 0; i < 64; i++) { ga[i] = 0.f; gb[i] = 0.f; }
          uint32_t a[2][16];
          const uint32_t l = fresh_lane();
          uint32_t fa[4];
#pragma unroll
          for (int kk = 0; kk < 4; kk++) fa[kk] = (base + wg * 8192 + frag_offset(warp)) ^ (kk * 32);
          const uint32_t mt = par + (l & 3) * 16;
          auto fetch = [&](int i, uint32_t (&f)[16], uint32_t z) {
            mbar_wait(xfull + (i & 3) * 8, i >> 2);
#pragma unroll
            for (int kk = 0; kk < 4; kk++) ldmatrix4(fa[kk] + (i & 3) * GST_BYTES + z, f[4 * kk], f[4 * kk + 1], f[4 * kk + 2], f[4 * kk + 3]);
          };
          const bool oddw = warp & 2;
          uint4 r0, r1;
          {
            const uint32_t t7 = (warp & 1) * 64 + (l >> 4) * 32 + (l & 15);
            const uint32_t* pm = g_modp + wg * DM + ((cj * 128 + t7 * 4) & (DM - 1));
            const uint32_t* pr = g_ln1 + (rb * 128 + warp * 16 + (l >> 2)) * 4;
            uint4 m0 = make_uint4(tag, tag, tag, tag), m1 = m0;
            if (!oddw) { m0 = ld_relaxed4(pm); m1 = ld_relaxed4(pm + 2 * DM); }
            r0 = ld_b128(pr); r1 = ld_b128(pr + 32);
            fetch(0, a[0], 0); fetch(1, a[1], 0);
            uint32_t n = 0;
            bool written = false;
#pragma unroll 1
            while (true) {
              uint32_t miss;
              asm volatile("{ .reg .pred p0, p1, p2, p3; .reg .b32 t, u;\n"
                           "lop3.b32 t, %1, %2, %19, 0x7e; lop3.b32 u, %3, %4, %19, 0x7e; or.b32 t, t, u; and.b32 t, t, 3; setp.ne.u32 p0, t, 0;\n"
                           "lop3.b32 t, %5, %6, %19, 0x7e; lop3.b32 u, %7, %8, %19, 0x7e; or.b32 t, t, u; and.b32 t, t, 3; setp.ne.u32 p1, t, 0;\n"
                           "setp.ne.u32 p2, %12, %19; setp.ne.u32 p3, %16, %19;\n"
                           "@p0 ld.relaxed.gpu.global.v4.u32 {%1, %2, %3, %4}, [%17];\n"
                           "@p1 ld.relaxed.gpu.global.v4.u32 {%5, %6, %7, %8}, [%17 + 8192];\n"
                           "@p2 ld.relaxed.gpu.global.v4.u32 {%9, %10, %11, %12}, [%18];\n"
                           "@p3 ld.relaxed.gpu.global.v4.u32 {%13, %14, %15, %16}, [%18 + 128];\n"
                           "or.pred p0, p0, p1; or.pred p2, p2, p3; vote.sync.any.pred p0, p0, 0xffffffff; vote.sync.any.pred p2, p2, 0xffffffff;\n"
                           "selp.u32 t, 1, 0, p0; selp.u32 u, 2, 0, p2; or.b32 %0, t, u; }"
                           : "=r"(miss), "+r"(m0.x), "+r"(m0.y), "+r"(m0.z), "+r"(m0.w), "+r"(m1.x), "+r"(m1.y), "+r"(m1.z), "+r"(m1.w),
                             "+r"(r0.x), "+r"(r0.y), "+r"(r0.z), "+r"(r0.w), "+r"(r1.x), "+r"(r1.y), "+r"(r1.z), "+r"(r1.w)
                           : "l"(pm), "l"(pr), "r"(tag) : "memory");
              if (!(miss & 1) && !written) {
                written = true;
                if (!oddw) write_table(par, wg, t7, m0, m1);
                mbar_arrive(bar_mod);
              }
              if (!miss) break;
              watchdog(n);
            }
          }
          const uint32_t zero = r0.w ^ tag;
          auto normalize = [&](uint32_t (&f)[16]) {
#pragma unroll
            for (int k = 0; k < 16; k += 2) { f[k] = ln_norm(f[k], r0.x, r0.y, r0.z); f[k + 1] = ln_norm(f[k + 1], r1.x, r1.y, r1.z); }
          };
          auto modulate = [&](int i, uint32_t (&f)[16]) {
#pragma unroll
            for (int kk = 0; kk < 4; kk++) {
              const uint4 m = lds4(mt + slice_of(i) * 256 + kk * 64);
              f[4 * kk] = MODUL(f[4 * kk], m.x, m.z); f[4 * kk + 1] = MODUL(f[4 * kk + 1], m.x, m.z);
              f[4 * kk + 2] = MODUL(f[4 * kk + 2], m.y, m.w); f[4 * kk + 3] = MODUL(f[4 * kk + 3], m.y, m.w);
            }
            keep(f);
            mbar_arrive_pred(xempty + (i & 3) * 8, l == 0);
          };
          auto publish = [&](int u, uint32_t (&f)[16]) {
#pragma unroll
            for (int kk = 0; kk < 4; kk++) stmatrix4(fa[kk] + OFF_STAGE + u * UNIT, f[4 * kk], f[4 * kk + 1], f[4 * kk + 2], f[4 * kk + 3]);
            __syncwarp();
            mbar_arrive_pred(bar_hpub + u * 8, l == 0);
          };
          auto multiply = [&](int i, uint32_t (&f)[16]) {
            mbar_wait(gfull + (i & 3) * 8, i >> 2);
            const uint64_t db = make_desc(base + (i & 3) * GST_BYTES + UNIT, 8192, 1024);
            wg_fence();
#pragma unroll
            for (int kk = 0; kk < 4; kk++) mma256_rs(ga, gb, f[4 * kk], f[4 * kk + 1], f[4 * kk + 2], f[4 * kk + 3], db + kk * 128);
            wg_commit();
          };
          auto next = [&](int i, uint32_t (&f)[16]) {
            wg_wait<1>();
            mbar_arrive_cl(rempty, GE + ((i + 2) & 3) * 8);
            uint32_t z = zero;
#pragma unroll
            for (int k = 0; k < 16; k += 2) asm volatile("lop3.b32 %0, %1, %2, %0, 0xA8;" : "+r"(z) : "r"(f[k]), "r"(f[k + 1]));
            fetch(i, f, z);
            normalize(f);
            if (i == 2) { keep(f); mbar_wait(bar_mod2, 0); }
            modulate(i, f); multiply(i, f);
          };
          normalize(a[0]); normalize(a[1]);
          keep(a[0]); keep(a[1]);
          mbar_wait(bar_mod, 0);
          PROF(1, tid == 0, 2);
          modulate(0, a[0]); multiply(0, a[0]); publish(0, a[0]);
          modulate(1, a[1]); multiply(1, a[1]);
#pragma unroll 1
          for (int i = 2; i < NRS; i += 2) {
            next(i, a[0]);
            if (i == 2) publish(1, a[0]);
            next(i + 1, a[1]);
          }
          wg_wait<1>();
          mbar_arrive_cl(rempty, GE + ((NRS + 2) & 3) * 8);
#pragma unroll 1
          for (int i = NRS; i < 14; i++) {
            mbar_wait(xfull + (i & 3) * 8, (i >> 2) & 1);
            mbar_wait(gfull + (i & 3) * 8, (i >> 2) & 1);
            const uint32_t xa = base + (i & 3) * GST_BYTES;
            const uint64_t da = make_desc(xa + wg * 8192, 16, 1024), db = make_desc(xa + UNIT, 8192, 1024);
            if (i == 13) bar_sync(2 + wg, 256);
            wg_fence();
#pragma unroll
            for (int kk = 0; kk < 4; kk++) mma256_ss(ga, gb, da + kk * 2, db + kk * 128, 1);
            wg_commit();
            if (i == 13) bar_arrive(3 - wg, 256);
            wg_wait<1>();
            uint32_t z = zero;
#pragma unroll
            for (int k = 0; k < 16; k += 2) asm volatile("lop3.b32 %0, %1, %2, %0, 0xA8;" : "+r"(z) : "r"(a[1][k]), "r"(a[1][k + 1]));
            mbar_arrive_cl(rempty, GE + ((i + 3) & 3) * 8 + z);
            mbar_arrive_pred(xempty + ((i + 3) & 3) * 8, l == 0 && i != NRS);
          }
          mbar_wait(xfull + 16, 1);
          wg_wait<0>();
          keep(ga); keep(gb);
#pragma unroll
          for (int i = 0; i < 64; i++) {
            asm volatile("mov.b32 %0, %1;" : "=f"(s[i]) : "f"(ga[i]));
            asm volatile("mov.b32 %0, %1;" : "=f"(o[i]) : "f"(gb[i]));
          }
        } else {
          float ga[64], gb[64];
#pragma unroll
          for (int i = 0; i < 64; i++) {
            asm volatile("mov.b32 %0, %1;" : "=f"(ga[i]) : "f"(s[i]));
            asm volatile("mov.b32 %0, %1;" : "=f"(gb[i]) : "f"(o[i]));
          }
#pragma unroll 1
          for (int i = 0; i < nst; i++) {
            mbar_wait(gfull + (i & 3) * 8, (i >> 2) & 1);
            const uint64_t da = make_desc(base + unit_of(ps == 2 && (i >> 2) == 1 ? XT2B : xt, i & 3) + wg * 8192, 16, 1024), db = make_desc(base + unit_of(wt, i & 3), 8192, 1024);
            if (i == nst - 1) bar_sync(2 + wg, 256);
            wg_fence();
#pragma unroll
            for (int kk = 0; kk < 4; kk++) mma256_ss(ga, gb, da + kk * 2, db + kk * 128, kk ? 1 : i);
            wg_commit();
            if (i == nst - 1) bar_arrive(3 - wg, 256);
            wg_wait<1>();
            mbar_arrive_cl(rempty, GE + ((i + 3) & 3) * 8, i != 0);
            PROF(4, tid == 0 && (i & 3) == 0, 40 + (ps - 1) * 4 + i / 4);
          }
          wg_wait<0>();
          keep(ga); keep(gb);
#pragma unroll
          for (int i = 0; i < 64; i++) {
            asm volatile("mov.b32 %0, %1;" : "=f"(s[i]) : "f"(ga[i]));
            asm volatile("mov.b32 %0, %1;" : "=f"(o[i]) : "f"(gb[i]));
          }
        }
        mbar_arrive_cl(rempty, GE + (ps == 2 ? 24 : 8));
        if (ps == 2) break;
      }
      const uint32_t qw = base + wg * 8192, qt = QT >> (16 * ps), at = ps ? AT1 : AT0;
      {
        const uint32_t wt = ps ? WT1 : WT0;
        const uint64_t da0 = make_desc(qw + unit_of(qt, 2), 16, 1024), da1 = make_desc(qw + unit_of(qt, 3), 16, 1024);
        const uint64_t db0 = make_desc(base + unit_of(wt, 2), 8192, 1024), db1 = make_desc(base + unit_of(wt, 3), 8192, 1024);
        mbar_wait(gfull + 16, 1);
        bar_sync(2 + wg, 256);
        wg_fence();
#pragma unroll
        for (int kk = 0; kk < 4; kk++) mma_ss<1>(s, da0 + kk * 2, db0 + kk * 128, 1);
        wg_commit();
        mbar_wait(xfull + 24, 1);
        mbar_wait(gfull + 24, 1);
        wg_fence();
#pragma unroll
        for (int kk = 0; kk < 4; kk++) mma_ss<1>(s, da1 + kk * 2, db1 + kk * 128, 1);
        wg_commit();
        bar_arrive(3 - wg, 256);
        mbar_wait(ps == 0 ? bar_pread : bar_ofree + 8, 0);
        wg_wait<0>();
        keep(s);
        PROF(2, tid == 0, 8 + ps * 8);
        uint32_t q[32];
        pack_p(s, q);
#pragma unroll
        for (int i = 0; i < 4; i++) stmatrix4((qw + unit_of(qt, 0) + frag_offset(warp)) ^ (i << 5), q[4 * i], q[4 * i + 1], q[4 * i + 2], q[4 * i + 3]);
        keep(q);
        bar_sync(2 + wg, 256);
        wg_fence();
#pragma unroll
        for (int kk = 0; kk < 8; kk++) mma_ss<1>(o, (kk < 4 ? da0 : da1) + (kk & 3) * 2, (kk < 4 ? db0 : db1) + UNIT / 16 + (kk & 3) * 128, 1);
        wg_commit();
        mbar_wait(bfull, 0);
        wg_fence();
        const uint64_t dk = make_desc(base + unit_of(at, 0), 16, 1024);
#pragma unroll
        for (int kk = 0; kk < 8; kk++) mma_rs<0>(s, q[4 * kk], q[4 * kk + 1], q[4 * kk + 2], q[4 * kk + 3], dk + (kk >> 2) * 1024 + (kk & 3) * 2, kk != 0);
        wg_commit();
        bar_arrive(3 - wg, 256);
#pragma unroll
        for (int i = 4; i < 8; i++) stmatrix4((qw + unit_of(qt, 1) + frag_offset(warp)) ^ ((i & 3) << 5), q[4 * i], q[4 * i + 1], q[4 * i + 2], q[4 * i + 3]);
        wg_wait<1>();
        keep(o);
        mbar_arrive_cl(rempty, GE + 16);
        mbar_arrive_cl(rempty, GE + 24);
        store_chunk<0>(o, qw + unit_of(qt, 2) + frag_offset(warp));
        store_chunk<1>(o, qw + unit_of(qt, 3) + frag_offset(warp));
        wg_wait<0>();
        keep(s);
        mbar_arrive_cl(rempty, 0);
      }
      PROF(4, tid == 0 && ps == 1, 61);
      float l0 = 0.f, l1 = 0.f;
      auto step = [&](auto odd_c, const int j, uint32_t (&pw)[32], uint32_t (&pr)[32]) {
        constexpr bool ODD = decltype(odd_c)::value;
        const bool first = !ODD && (j & 2) == 0, last = ODD && j == 7;
        const uint32_t ph = (j >> 1) & 1;
        float i0, i1, a0, a1;
        const bool so = !ODD && j == 4;
        if (so) { i0 = inv_quad_sum(l0); i1 = inv_quad_sum(l1); l0 = 0.f; l1 = 0.f; }
        bool redo = !ODD && (j | ps) == 0;
        while (true) {
          if (redo) {
            float m0 = fmaxf(s[0], s[1]), m1 = fmaxf(s[2], s[3]);
#pragma unroll
            for (int i = 1; i < 16; i++) { m0 = fmaxf(m0, fmaxf(s[4 * i], s[4 * i + 1])); m1 = fmaxf(m1, fmaxf(s[4 * i + 2], s[4 * i + 3])); }
            m0 = fmaxf(m0, __shfl_xor_sync(0xffffffffu, m0, 1)); m1 = fmaxf(m1, __shfl_xor_sync(0xffffffffu, m1, 1));
            m0 = fmaxf(m0, __shfl_xor_sync(0xffffffffu, m0, 2)); m1 = fmaxf(m1, __shfl_xor_sync(0xffffffffu, m1, 2));
            m0 *= SCL2; m1 *= SCL2;
            if (!first) {
              m0 = fmaxf(m0, f0); m1 = fmaxf(m1, f1);
              const float c0 = ex2(f0 - m0), c1 = ex2(f1 - m1);
              l0 *= c0; l1 *= c1;
              wg_wait<0>();
              keep(o);
#pragma unroll
              for (int i = 0; i < 16; i++) { o[4 * i] *= c0; o[4 * i + 1] *= c0; o[4 * i + 2] *= c1; o[4 * i + 3] *= c1; }
            }
            f0 = m0; f1 = m1;
          }
          float b0 = 0.f, b1 = 0.f;
          a0 = 0.f; a1 = 0.f;
#pragma unroll
          for (int i = 0; i < 16; i++) {
            const float e0 = ex2(fmaf(s[4 * i], SCL2, -f0)), e1 = ex2(fmaf(s[4 * i + 1], SCL2, -f0));
            const float e2 = ex2(fmaf(s[4 * i + 2], SCL2, -f1)), e3 = ex2(fmaf(s[4 * i + 3], SCL2, -f1));
            a0 += e0; b0 += e1; a1 += e2; b1 += e3;
            pw[2 * i] = pack_bf(e0, e1); pw[2 * i + 1] = pack_bf(e2, e3);
            if (i == VREL) {
#pragma unroll
              for (int k = 0; k < 2 * VREL + 2; k++) asm volatile("" : "+r"(pw[k])::"memory");
              mbar_wait(bar_mod, 0);
              wg_wait<0>();
              mbar_arrive_cl(rempty, ODD ? 16 : 0, !redo && (ODD || j));
#pragma unroll
              for (int k = 4 * VREL + 4; k < 64; k++) asm volatile("" : "+f"(s[k])::"memory");
            }
          }
          a0 += b0; a1 += b1;
          if (redo) break;
          redo = __any_sync(0xffffffffu, !(a0 + a1 < 0x1p90f));
          if (first) {
            uint32_t m0 = __ballot_sync(0xffffffffu, a0 > 0x1p-80f), m1 = __ballot_sync(0xffffffffu, a1 > 0x1p-80f);
            m0 |= m0 >> 1; m1 |= m1 >> 1; m0 |= m0 >> 2; m1 |= m1 >> 2;
            redo = redo || (m0 & m1 & 0x11111111u) != 0x11111111u;
          }
          if (!redo) break;
        }
        l0 += a0; l1 += a1;
        keep(pw);
        keep(o);
        if (so) store_chunk<0>(o, i0, i1, qw + unit_of(qt, 0) + frag_offset(warp));
        keep(o);
        if (j == (ODD ? 5 : 0)) { fence_async_smem(); if (ODD) mbar_arrive(bar_ofull + wg * 8); }
        mbar_wait(bfull + (ODD ? 24 : 8), ph);
        bar_sync(2 + wg, 256);
        if (!last) {
          const uint32_t qn = qt >> (j >= 3 ? 8 : 0);
          wg_fence();
          issue_qk(s, qw + unit_of(qn, 0), qw + unit_of(qn, 1), base + unit_of(at, ODD ? 3 : 1));
          wg_commit();
          mbar_wait(bfull + (ODD ? 0 : 16), ODD ? ph ^ 1 : ph);
        }
        if (so) { store_chunk<1>(o, i0, i1, qw + unit_of(qt, 1) + frag_offset(warp)); keep(o); }
        wg_fence();
        issue_pv(o, pw, base + unit_of(at, ODD ? (last ? 3 : 0) : 2), !first);
        wg_commit();
        bar_arrive(3 - wg, 256);
        wg_wait<1>();
        keep(s);
        mbar_arrive_cl(rempty, ODD ? 24 : 8, !last);
        PROF(4, tid == 0 && ps == 1, 51 + j);
      };
      uint32_t pa[32], pb[32];
#pragma unroll 1
      for (int j = 0; j < 8; j += 2) {
        step(std::false_type{}, j, pa, pb);
        step(std::true_type{}, j + 1, pb, pa);
      }
      {
        const float i0 = inv_quad_sum(l0), i1 = inv_quad_sum(l1);
        wg_wait<0>();
        keep(o);
        mbar_arrive_cl(rempty, 24);
        store_chunk<0>(o, i0, i1, qw + unit_of(qt, 2) + frag_offset(warp));
        store_chunk<1>(o, i0, i1, qw + unit_of(qt, 3) + frag_offset(warp));
        fence_async_smem();
        mbar_arrive(bar_ofull + 16 + wg * 8);
      }
      PROF(2, tid == 0, 10 + ps * 8);
    }

    const int ln = fresh_lane(), g = ln >> 2, tq = ln & 3, ct = warp * 32 + ln;
    const bool lane0 = ln == 0;
    const int lrow0 = warp * 16 + g;
    const int grow0 = rb * 128 + lrow0;
    const uint32_t res = base + OFF_RES, trow = res + wg * 8192 + frag_offset(warp);
    uint32_t xr[32];
    uint4 sv[4], own;
    uint32_t* sp[4];
#pragma unroll
    for (int k = 0; k < 4; k++) sp[k] = g_stats + ((((tq >> 1) * 4 + k) ^ cj) * SEQ + grow0 + (tq & 1) * 8) * 4;
    {
      const uint64_t da = make_desc(base + wg * 8192, 16, 1024), db = make_desc(base, 8192, 1024);
      constexpr int U = UNIT / 16;
#define HALF_STAGE(acc, xu, wu) _Pragma("unroll") for (int kk = 0; kk < 4; kk++) mma_ss<1>(acc, da + (xu) * U + kk * 2, db + (wu) * U + kk * 128, 1)
      PROF(10, ct == PT, 19); STAMP(0);
      cluster_arrive();
      mbar_wait(gfull, 1);
      mbar_wait(gfull + 8, 1);
      bar_sync(2 + wg, 256);
      wg_fence();
      HALF_STAGE(o, 7, 1);
      HALF_STAGE(o, 8, 3);
      wg_commit();
      STAMP(16);
      mbar_wait(gfull + 16, 1);
      STAMP(17);
      wg_fence();
      HALF_STAGE(o, 6, 11);
      wg_commit();
      bar_arrive(3 - wg, 256);
      mbar_wait(bar_par, 0);
      uint32_t* xo = g_xch + ((size_t)b * 8 * 256 + ct) * 4;
      const uint32_t* xi = g_xch + ((size_t)(b ^ 2) * 8 * 256 + ct) * 4;
      const uint32_t par1 = (~lds1(par + PAR_CONST + 4) & 1) << 16;
      wg_wait<1>();
      mbar_arrive_pred(bar_rel, lane0);
      wg_wait<0>();
      keep(o);
      mbar_arrive_pred(bar_ring, lane0);
      PROF(8, ct == PT, 20); STAMP(1);
#define SEND(i) st_b128(xo + (i) * 1024, (pack_bf(o[8 * (i)], o[8 * (i) + 1]) & ~0x10000u) | par1, pack_bf(o[8 * (i) + 2], o[8 * (i) + 3]), \
                        pack_bf(o[8 * (i) + 4], o[8 * (i) + 5]), pack_bf(o[8 * (i) + 6], o[8 * (i) + 7]))
#pragma unroll
      for (int i = 0; i < NS1; i++) SEND(i);
      PROF(8, ct == PT, 21); STAMP(2);
      bar_sync(2 + wg, 256);
      wg_fence();
      HALF_STAGE(s, 7, 0);
      HALF_STAGE(s, 8, 2);
      HALF_STAGE(s, 6, 10);
      wg_commit();
      bar_arrive(3 - wg, 256);
      STAMP(18);
      mbar_wait(gfull + 24, 1);
#pragma unroll
      for (int i = NS1; i < 8; i++) SEND(i);
      uint4 v[8];
#pragma unroll
      for (int i = 0; i < LD1; i++) v[i] = ld_b128(xi + i * 1024);
      STAMP(19);
      mbar_wait(bar_xres, 0);
      wg_wait<0>();
      mbar_arrive_pred(bar_ring + 8, lane0);
      bar_sync(2 + wg, 256);
      STAMP(20);
#pragma unroll
      for (int i = LD1; i < LD2; i++) v[i] = ld_b128(xi + i * 1024);
      mbar_wait(bar_xres, 0);
      wg_fence();
      HALF_STAGE(s, 9, 4);
      wg_commit();
      mbar_wait(bar_rx, 0);
      wg_fence();
      HALF_STAGE(s, 1, 5);
      wg_commit();
      bar_arrive(3 - wg, 256);
      STAMP(21);
#pragma unroll
      for (int i = LD2; i < 8; i++) v[i] = ld_b128(xi + i * 1024);
      if (LD2 < 8) mbar_wait(bar_xres, 0);
      wg_wait<0>();
      keep(s);
      mbar_arrive_pred(bar_ring + 16, lane0);
      PROF(10, ct == PT, 23); STAMP(4);
#pragma unroll
      for (int i = 0; i < 16; i += 2) ldmatrix4((trow ^ ((i & 7) << 4)) + (i >> 3) * 16384, xr[2 * i], xr[2 * i + 1], xr[2 * i + 2], xr[2 * i + 3]);
      uint32_t ga[16];
      uint4 bw[8];
#pragma unroll
      for (int i = 0; i < 8; i++) {
        if (!(i & 1)) {
          const uint4 t = lds4(par + PAR_SINK + i * 32 + tq * 16);
          ga[2 * i] = t.x; ga[2 * i + 1] = t.y; ga[2 * i + 2] = t.z; ga[2 * i + 3] = t.w;
        }
        bw[i] = lds4(par + PAR_T1 + i * 64 + tq * 16);
        if (!(g & 1)) { bw[i].x = 0x3f803f80u; bw[i].y = 0x3f803f80u; }
      }
      uint32_t pk[32];
      pack_p(s, pk);
      keep(pk);
      {
        uint32_t n = 0, miss;
        do {
          miss = 0;
#pragma unroll
          for (int i = 0; i < 8; i++) miss |= v[i].x ^ par1;
          miss = __any_sync(0xffffffffu, miss & 0x10000u);
          if (miss) {
#pragma unroll
            for (int i = 0; i < 8; i++)
              asm volatile("{ .reg .pred p; .reg .b32 t; xor.b32 t, %0, %5; and.b32 t, t, 0x10000; setp.ne.u32 p, t, 0;\n"
                           "@p ld.relaxed.gpu.global.v4.u32 {%0, %1, %2, %3}, [%4]; }"
                           : "+r"(v[i].x), "+r"(v[i].y), "+r"(v[i].z), "+r"(v[i].w) : "l"(xi + i * 1024), "r"(par1) : "memory");
          }
          watchdog(n);
        } while (miss);
      }
      PROF(8, ct == PT, 22); STAMP(3);
      float ds[4] = {0.f, 0.f, 0.f, 0.f}, dl[4] = {0.f, 0.f, 0.f, 0.f}, q0[4] = {0.f, 0.f, 0.f, 0.f}, q1[4] = {0.f, 0.f, 0.f, 0.f};
#pragma unroll
      for (int i = 0; i < 8; i++) {
        const uint32_t u0 = hfma2(ga[2 * i], hadd2(pk[4 * i], v[i].x & ~0x10000u), xr[4 * i]);
        const uint32_t u1 = hfma2(ga[2 * i], hadd2(pk[4 * i + 1], v[i].y), xr[4 * i + 1]);
        const uint32_t u2 = hfma2(ga[2 * i + 1], hadd2(pk[4 * i + 2], v[i].z), xr[4 * i + 2]);
        const uint32_t u3 = hfma2(ga[2 * i + 1], hadd2(pk[4 * i + 3], v[i].w), xr[4 * i + 3]);
        xr[4 * i] = u0; xr[4 * i + 1] = u1; xr[4 * i + 2] = u2; xr[4 * i + 3] = u3;
        mma16816(ds, u0, u1, u2, u3, bw[i].x, bw[i].y);
        mma16816(dl, u0, u1, u2, u3, bw[i].z, bw[i].w);
        mma16816(q0, u0, u1, u2, u3, u0, u2);
        mma16816(q1, u0, u1, u2, u3, u1, u3);
      }
      const float sqa = __shfl_sync(0xffffffffu, (g & 1) ? q0[1] : q0[0], g * 4 + (g >> 1));
      const float sqb = __shfl_sync(0xffffffffu, (g & 1) ? q1[3] : q1[2], g * 4 + (g >> 1));
      own = (tq & 1) ? make_uint4(__float_as_uint(ds[2]), __float_as_uint(sqb), __float_as_uint(ds[3] + dl[3]), tag)
                                 : make_uint4(__float_as_uint(ds[0]), __float_as_uint(sqa), __float_as_uint(ds[1] + dl[1]), tag);
      if (tq < 2) st_b128(sp[0], own.x, own.y, own.z, own.w);
#pragma unroll
      for (int k = 0; k < 4; k++) sv[k] = make_uint4(0, 0, 0, 0);
    }
    PROF(8, ct == PT, 29); STAMP(5);
    uint32_t mm, ih, il;
    float rbest;
    uint32_t wf[128];
    const uint32_t frow = (ln & 7) + (ln >> 4) * 8;
    const uint32_t wfo = base + (warp & 1) * 8192 + frow * 64 + ((((ln >> 3) & 1) ^ ((frow >> 1) & 3)) << 4);
#define LOAD_WF(m) _Pragma("unroll") for (int f = 0; f < 16; f++) {                                                   \
      const int r = ((f >> 1) * 4 + (m) * 2 + (f & 1)) * 4;                                                           \
      ldmatrix4t(((wfo + unit_of((m) ? FT_U : FT_G, warp >> 1)) ^ ((f & 1) * 32)) + (f >> 1) * 1024, wf[r], wf[r + 1], wf[r + 2], wf[r + 3]); \
    }
    bool early;
    {
#pragma unroll
      for (int i = 0; i < 16; i += 2) stmatrix4((trow ^ ((i & 7) << 4)) + (i >> 3) * 16384, xr[2 * i], xr[2 * i + 1], xr[2 * i + 2], xr[2 * i + 3]);
      const uint4 cst = lds4(par + PAR_CONST);
      const float A1 = __uint_as_float(cst.x), A2 = __uint_as_float(cst.z);
      uint32_t n = 0;
      early = false;
#pragma unroll 1
      while (true) {
        uint32_t miss;
        asm volatile("{ .reg .pred p0, p1, p2, p3; .reg .b64 u, v; .reg .b128 w;\n"
                     "setp.ge.u32 p0, %22, 2; setp.ne.and.u32 p0, %4, %21, p0; setp.ne.u32 p1, %8, %21; setp.ne.u32 p2, %12, %21; setp.ne.u32 p3, %16, %21;\n"
                     "@p0 ld.relaxed.gpu.global.v4.u32 {%1, %2, %3, %4}, [%17];\n"
                     "@p1 ld.relaxed.gpu.global.v4.u32 {%5, %6, %7, %8}, [%18];\n"
                     "@p2 ld.relaxed.gpu.global.v4.u32 {%9, %10, %11, %12}, [%19];\n"
                     "@p3 ld.relaxed.gpu.global.v4.u32 {%13, %14, %15, %16}, [%20];\n"
                     "or.pred p0, p0, p1; or.pred p2, p2, p3; or.pred p0, p0, p2; vote.sync.any.pred p0, p0, 0xffffffff; selp.u32 %0, 1, 0, p0; }"
                     : "=r"(miss), "+r"(sv[0].x), "+r"(sv[0].y), "+r"(sv[0].z), "+r"(sv[0].w), "+r"(sv[1].x), "+r"(sv[1].y), "+r"(sv[1].z), "+r"(sv[1].w),
                       "+r"(sv[2].x), "+r"(sv[2].y), "+r"(sv[2].z), "+r"(sv[2].w), "+r"(sv[3].x), "+r"(sv[3].y), "+r"(sv[3].z), "+r"(sv[3].w)
                     : "l"(sp[0]), "l"(sp[1]), "l"(sp[2]), "l"(sp[3]), "r"(tag), "r"(tq) : "memory");
        if (!miss) break;
        if (!early && (b >= NFFN || __all_sync(0xffffffffu, mbar_test(bar_box + (warp >> 1) * 8, 0)))) {
          early = true;
          LOAD_WF(0);
          __syncwarp();
          mbar_arrive_pred(bar_gate, lane0);
        }
        watchdog(n);
      }
      const uint4 v0 = tq < 2 ? own : sv[0], v1 = sv[1], v2 = sv[2], v3 = sv[3];
      PROF(8, ct == PT, 30); STAMP(6);
      float su = (__uint_as_float(v0.x) + __uint_as_float(v1.x)) + (__uint_as_float(v2.x) + __uint_as_float(v3.x));
      float sq = (__uint_as_float(v0.y) + __uint_as_float(v1.y)) + (__uint_as_float(v2.y) + __uint_as_float(v3.y));
      float dt = (__uint_as_float(v0.z) + __uint_as_float(v1.z)) + (__uint_as_float(v2.z) + __uint_as_float(v3.z));
      su += __shfl_xor_sync(0xffffffffu, su, 2); sq += __shfl_xor_sync(0xffffffffu, sq, 2); dt += __shfl_xor_sync(0xffffffffu, dt, 2);
      const float m = su * (1.f / DM);
      float mb, sd;
      ln_scalars(m, fmaxf(sq * (1.f / DM) - m * m, 0.f), mb, sd);
      const float inv = rcp(sd);
      rbest = (dt - mb * A1) * inv + A2;
      mm = pack_bf(mb, mb);
      ih = pack_bf(inv, inv);
      const float lo = inv - bf_lo(ih);
      il = pack_bf(lo, lo);
    }
    int ibest;
    {
      const uint32_t bits = __float_as_uint(rbest);
      const uint32_t key = (((int)bits < 0 ? ~bits : bits | 0x80000000u) & ~0x1ffu) | ((127 - lrow0 - (tq & 1) * 8) << 2) | tag;
      sts1(par + PAR_RED + warp * 4, __reduce_max_sync(0xffffffffu, key));
      PROF(8, ct == PT, 38); STAMP(7);
      bar_sync(1, 256);
      const uint4 ka = lds4(par + PAR_RED), kb = lds4(par + PAR_RED + 16);
      const uint32_t k2 = max(max(max(ka.x, ka.y), max(ka.z, ka.w)), max(max(kb.x, kb.y), max(kb.z, kb.w)));
      if (ct < CR && cj == 0) st_relaxed(g_cand + ct * 512 + rb * CS, k2);
      ibest = 127 - ((k2 >> 2) & 127);
    }
    PROF(8, ct == PT, 39); STAMP(8);
    if ((ibest >> 4) == warp) {
      const int src = (ibest & 7) * 4 + ((ibest >> 3) & 1), ch = g * 2;
      const uint32_t cm = __shfl_sync(0xffffffffu, mm, src), ch_ = __shfl_sync(0xffffffffu, ih, src), cl = __shfl_sync(0xffffffffu, il, src);
      const uint32_t xa = res + (ch >> 3) * 16384 + ibest * 128 + (((ch & 7) ^ (ibest & 7)) << 4) + tq * 4;
      const uint32_t x0 = lds1(xa), x1 = lds1(xa ^ 16);
      const uint2 p0 = lds2(par + PAR_T2 + ch * 64 + tq * 16), p1 = lds2(par + PAR_T2 + ch * 64 + 64 + tq * 16);
      uint32_t* dst = g_row + rb * 2 * DM + cj * 128 + ln * 4;
      st_pairs(dst, ln_mod(x0, cm, ch_, cl, p0.x, p0.y), ln_mod(x1, cm, ch_, cl, p1.x, p1.y), tag);
      st_pairs(dst + DM, x0, x1, tag);
      __syncwarp();
    }
    PROF(8, ct == PT, 37); STAMP(9);
    uint32_t wd[64];
    const uint32_t wda = base + unit_of(FT_D, warp >> 1) + (warp & 1) * 8192 + frow * 128 + ((((ln >> 3) & 1) ^ (ln & 7)) << 4);
#define LOAD_WD(f) ldmatrix4t((wda ^ ((((f) >> 1) & 3) * 32)) + ((f) >> 3) * 4096 + ((f) & 1) * 2048, wd[4 * (f)], wd[4 * (f) + 1], wd[4 * (f) + 2], wd[4 * (f) + 3])
    if (!early) {
      if (b < NFFN) mbar_wait(bar_box + (warp >> 1) * 8, 0);
      LOAD_WF(0);
      __syncwarp();
      mbar_arrive_pred(bar_gate, lane0);
    }
    if (b < NFFN) {
      const uint32_t own = base + unit_of(FT_G, warp >> 1) + (warp & 1) * 8192;
      mbar_wait(bar_box + (4 + (warp >> 1)) * 8, 0);
      LOAD_WF(1);
      uint32_t* const ydst = ypart_slot(b, warp * 16 + (tq & 1) * 8 + g);
      PROF(8, ct == PT, 31); STAMP(10);
      bool wdok;
      {
        uint32_t n = 0;
        while (!(wdok = __all_sync(0xffffffffu, mbar_test(bar_box + (8 + (warp >> 1)) * 8, 0))) && !__all_sync(0xffffffffu, mbar_test(bar_sel, 0))) watchdog(n);
      }
      if (wdok) {
#pragma unroll
        for (int f = 0; f < 16; f++) LOAD_WD(f);
      }
      STAMP(11);
      mbar_wait(bar_sel, 0);
      PROF(8, ct == PT, 33); STAMP(12);
      float d[8][4];
#pragma unroll
      for (int i = 0; i < 4; i++) { d[i][0] = 0.f; d[i][1] = 0.f; d[i][2] = 0.f; d[i][3] = 0.f; }
#pragma unroll
      for (int ks = 0; ks < 8; ks++) {
        const uint2 hb = lds2(own + 256 + ks * 32 + tq * 8);
#pragma unroll
        for (int mt = 0; mt < 4; mt++) {
          const int r = ks * 16 + mt * 4;
          mma16816(d[mt], wf[r], wf[r + 1], wf[r + 2], wf[r + 3], hb.x, hb.y);
        }
      }
      sts2(own + (tq * 8 + g) * 8, __float_as_uint((tq & 2) ? ((tq & 1) ? d[1][2] : d[1][0]) : ((tq & 1) ? d[0][2] : d[0][0])),
           __float_as_uint((tq & 2) ? ((tq & 1) ? d[3][2] : d[3][0]) : ((tq & 1) ? d[2][2] : d[2][0])));
      bar_sync(1, 256);
      uint32_t ab[4];
      {
        float G = 0.f, U = 0.f;
        uint2 pv[8];
#pragma unroll
        for (int w8 = 0; w8 < 8; w8++) pv[w8] = lds2(base + ln * 8 + ((FT_G >> (w8 >> 1) * 4) & 15) * UNIT + (w8 & 1) * 8192);
#pragma unroll
        for (int w8 = 0; w8 < 8; w8 += 2) {
          G += __uint_as_float(pv[w8].x) + __uint_as_float(pv[w8 + 1].x);
          U += __uint_as_float(pv[w8].y) + __uint_as_float(pv[w8 + 1].y);
        }
        const float act = rbf(silu_f(rbf(G))) * rbf(U);
        const uint32_t pk = pack_bf(act, __shfl_down_sync(0xffffffffu, act, 1));
#pragma unroll
        for (int i = 0; i < 4; i++) ab[i] = __shfl_sync(0xffffffffu, pk, i * 8 + tq * 2);
      }
      if (!wdok) {
        mbar_wait(bar_box + (8 + (warp >> 1)) * 8, 0);
#pragma unroll
        for (int f = 0; f < 16; f++) LOAD_WD(f);
      }
      PROF(8, ct == PT, 34); STAMP(13);
#pragma unroll
      for (int mt = 0; mt < 8; mt++) {
        d[mt][0] = 0.f; d[mt][1] = 0.f; d[mt][2] = 0.f; d[mt][3] = 0.f;
        mma16816(d[mt], wd[mt * 8], wd[mt * 8 + 1], wd[mt * 8 + 2], wd[mt * 8 + 3], ab[0], ab[1]);
        mma16816(d[mt], wd[mt * 8 + 4], wd[mt * 8 + 5], wd[mt * 8 + 6], wd[mt * 8 + 7], ab[2], ab[3]);
      }
      uint32_t yw[4];
#pragma unroll
      for (int i = 0; i < 4; i++) yw[i] = (tq & 1) ? pack_bf(d[2 * i][2], d[2 * i + 1][2]) : pack_bf(d[2 * i][0], d[2 * i + 1][0]);
      if (tq < 2) st_b128(ydst, (yw[0] & ~1u) | (tag & 1), (yw[1] & ~1u) | (tag >> 1), yw[2], yw[3]);
      PROF(8, ct == PT, 35); STAMP(14);
    }
    mbar_wait(bar_sel, 0);
    mbar_arrive_pred(bar_win, ct == 0);
    const int iwin = lds1(par + PAR_CONST + 60) & 0x7ff;
    const bool cand = (iwin >> 4) == rb * 8 + warp;
    {
      const uint32_t mm0 = __shfl_sync(0xffffffffu, mm, ln & ~1), mm1 = __shfl_sync(0xffffffffu, mm, ln | 1);
      const uint32_t ih0 = __shfl_sync(0xffffffffu, ih, ln & ~1), ih1 = __shfl_sync(0xffffffffu, ih, ln | 1);
      const uint32_t il0 = __shfl_sync(0xffffffffu, il, ln & ~1), il1 = __shfl_sync(0xffffffffu, il, ln | 1);
#pragma unroll OUR
      for (int hf = 0; hf < 2; hf++) {
        uint32_t x[16];
#pragma unroll
        for (int i = 0; i < 8; i += 2) ldmatrix4((trow ^ (i << 4)) + hf * 16384, x[2 * i], x[2 * i + 1], x[2 * i + 2], x[2 * i + 3]);
#pragma unroll
        for (int i = 0; i < 8; i++) {
          const uint4 pv = lds4(par + PAR_T2 + (hf * 8 + i) * 64 + tq * 16);
          x[2 * i] = hfma2(hfma2(ln_norm(x[2 * i], mm0, ih0, il0), pv.x, pv.y), pv.z, x[2 * i]);
          x[2 * i + 1] = hfma2(hfma2(ln_norm(x[2 * i + 1], mm1, ih1, il1), pv.x, pv.y), pv.z, x[2 * i + 1]);
        }
#pragma unroll
        for (int i = 0; i < 8; i += 2) stmatrix4((trow ^ (i << 4)) + hf * 16384, x[2 * i], x[2 * i + 1], x[2 * i + 2], x[2 * i + 3]);
        if (!cand) fence_async_smem();
        __syncwarp();
        if (!cand && elect_one()) {
          tma2d_store(&maps.out, res + hf * 16384 + warp * 2048, cj * 128 + hf * 64, rb * 128 + warp * 16);
          asm volatile("cp.async.bulk.commit_group;" ::: "memory");
        }
      }
    }
    if (cand) {
      const int wrow0 = warp * 16;
#pragma unroll 2
      for (int p = 0; p < 8; p++) {
        const int row = 2 * p + (ln >> 4), ch = ln & 15;
        const uint4 v = lds4(res + (ch >> 3) * 16384 + (wrow0 + row) * 128 + (((ch & 7) ^ (row & 7)) << 4));
        if (rb * 128 + wrow0 + row != iwin) *reinterpret_cast<uint4*>(P.out + (size_t)(rb * 128 + wrow0 + row) * DM + cj * 128 + ch * 8) = v;
      }
    }
    asm volatile("cp.async.bulk.wait_group.read 0;" ::: "memory");
    PROF(8, ct == PT, 11); STAMP(15);
    cluster_wait();
  }
}

typedef CUresult (*EncodeFn)(CUtensorMap*, CUtensorMapDataType, cuuint32_t, void*, const cuuint64_t*, const cuuint64_t*,
                             const cuuint32_t*, const cuuint32_t*, CUtensorMapInterleave, CUtensorMapSwizzle,
                             CUtensorMapL2promotion, CUtensorMapFloatOOBfill);

void map2d(EncodeFn enc, CUtensorMap* m, const void* p, uint64_t rows, uint64_t cols, uint32_t brows) {
  cuuint64_t dims[2] = {cols, rows}, strides[1] = {cols * 2};
  cuuint32_t box[2] = {64, brows}, es[2] = {1, 1};
  enc(m, CU_TENSOR_MAP_DATA_TYPE_BFLOAT16, 2, const_cast<void*>(p), dims, strides, box, es, CU_TENSOR_MAP_INTERLEAVE_NONE,
      CU_TENSOR_MAP_SWIZZLE_128B, CU_TENSOR_MAP_L2_PROMOTION_L2_256B, CU_TENSOR_MAP_FLOAT_OOB_FILL_NONE);
}
void map2d_narrow(EncodeFn enc, CUtensorMap* m, const void* p, uint64_t rows, uint64_t cols, uint32_t brows) {
  cuuint64_t dims[2] = {cols, rows}, strides[1] = {cols * 2};
  cuuint32_t box[2] = {32, brows}, es[2] = {1, 1};
  enc(m, CU_TENSOR_MAP_DATA_TYPE_BFLOAT16, 2, const_cast<void*>(p), dims, strides, box, es, CU_TENSOR_MAP_INTERLEAVE_NONE,
      CU_TENSOR_MAP_SWIZZLE_64B, CU_TENSOR_MAP_L2_PROMOTION_L2_64B, CU_TENSOR_MAP_FLOAT_OOB_FILL_NONE);
}
void map3d(EncodeFn enc, CUtensorMap* m, const void* p, uint64_t rows, uint64_t cols, uint32_t brows, uint32_t nch) {
  cuuint64_t dims[3] = {64, rows, cols / 64}, strides[2] = {cols * 2, 128};
  cuuint32_t box[3] = {64, brows, nch}, es[3] = {1, 1, 1};
  enc(m, CU_TENSOR_MAP_DATA_TYPE_BFLOAT16, 3, const_cast<void*>(p), dims, strides, box, es, CU_TENSOR_MAP_INTERLEAVE_NONE,
      CU_TENSOR_MAP_SWIZZLE_128B, CU_TENSOR_MAP_L2_PROMOTION_L2_256B, CU_TENSOR_MAP_FLOAT_OOB_FILL_NONE);
}

}

extern "C" void kernel_launch(void* const* d_in, const int* in_sizes, int n_in, void* d_out, int out_size) {
  (void)in_sizes; (void)n_in; (void)out_size;
  static EncodeFn enc = nullptr;
  if (!enc) {
    void* fn = nullptr;
    cudaDriverEntryPointQueryResult st;
    cudaGetDriverEntryPoint("cuTensorMapEncodeTiled", &fn, cudaEnableDefault, &st);
    enc = (EncodeFn)fn;
    cudaFuncSetAttribute(fused_kernel, cudaFuncAttributeMaxDynamicSharedMemorySize, SMEM_BYTES);
  }
  Maps maps;
  map2d(enc, &maps.x, d_in[0], SEQ, DM, 128);
  map2d(enc, &maps.out, d_out, SEQ, DM, 16);
  map3d(enc, &maps.wq, d_in[3], DM, NQ, 64, 2);
  map3d(enc, &maps.k, d_in[1], 4 * SK, 128, 128, 1);
  map3d(enc, &maps.v, d_in[2], 4 * SK, 128, 128, 1);
  map3d(enc, &maps.wo, d_in[4], NQ, DM, 64, 2);
  map2d_narrow(enc, &maps.wg, d_in[7], DM, FF, 256);
  map2d_narrow(enc, &maps.wu, d_in[8], DM, FF, 256);
  map3d(enc, &maps.wd, d_in[9], FF, DM, 32, 4);
  map2d_narrow(enc, &maps.wm, d_in[11], DM, NMOD, 256);
  Ptrs p;
  p.x = (const __nv_bfloat16*)d_in[0];
  p.w_r = (const __nv_bfloat16*)d_in[6];
  p.w_gate = (const __nv_bfloat16*)d_in[7];
  p.w_up = (const __nv_bfloat16*)d_in[8];
  p.w_down = (const __nv_bfloat16*)d_in[9];
  p.c = (const __nv_bfloat16*)d_in[10];
  p.w_mod = (const __nv_bfloat16*)d_in[11];
  p.out = (__nv_bfloat16*)d_out;
  fused_kernel<<<NMAIN + NHELP, 384, SMEM_BYTES>>>(maps, p);
}
```

```cpp
#include <cuda_runtime.h>
#include <cuda_bf16.h>
#include <cuda.h>
#include <stdint.h>
#include <type_traits>

#define HD 2
#define HDX 2
#define NRS 8
#define OSL 900
#define OSL2 400
#define VREL 5
#define OPS 8192
#define ODS1 5
#define ODS 8
#define PG0 15
#define WB 2
#define WN 20
#define HU 32
#define RES0 17
#define RES1 20
#define GOST 20
#define NS1 5
#define LD2 4
#define FPACE0 2
#define FPACE 3
#define CR 8
#define CS 8

namespace {

constexpr int SEQ = 2048, DM = 1024, NQ = 4096, SK = 2048, WIN = 512, FF = 3584, NMOD = 6144;
constexpr int NMAIN = 128, NHELP = 4, NFFN = 112;
constexpr int NSLOT = 4, SLOT_BYTES = 32768, UNIT = 16384, GST_BYTES = 3 * UNIT;
constexpr uint32_t XT1 = 0xDCBA, XT2 = 0x9687;
constexpr uint32_t WT0 = 0xA741, WT1 = 0x7420, WT2 = 0x4A20;
constexpr uint32_t AT0 = WT1, AT1 = WT2;
constexpr uint32_t QT = 0xDC9696DC;
constexpr int OFF_STAGE = 12 * UNIT;
constexpr uint32_t FT_G = 0x07B3, FT_U = 0xA628, FT_D = 0x5149;
constexpr int OFF_RES = 12 * UNIT;
constexpr int OFF_PAR = 14 * UNIT;
constexpr int OFF_BAR = OFF_PAR + 2528;
constexpr int SMEM_BYTES = OFF_BAR + 544;
static_assert(SMEM_BYTES <= 232448, "smem");

constexpr int PAR_T1 = 0;
constexpr int PAR_T2 = 512;
constexpr int PAR_CONST = 1536;
constexpr int PAR_RED = 1600;
constexpr int PAR_SINK = 2176;

struct Maps {
  CUtensorMap x, wq, k, v, wo, wg, wu, wd, wm, out;
};
struct Ptrs {
  const __nv_bfloat16 *x, *w_r, *c, *w_mod, *w_gate, *w_up, *w_down;
  __nv_bfloat16* out;
};

__device__ __align__(1024) uint8_t g_act[16 * 80 * UNIT];
__device__ __align__(128) uint32_t g_mod[NMOD];
__device__ __align__(128) uint32_t g_modp[2 * 2 * DM];
__device__ __align__(128) uint32_t g_ln1[SEQ * 4];
__device__ __align__(128) uint32_t g_cnt_h[16 * 32];
__device__ __align__(128) uint32_t g_cnt_o[128 * 32];
__device__ __align__(128) uint32_t g_xch[NMAIN * 8 * 256 * 4];
__device__ __align__(128) uint32_t g_stats[8 * SEQ * 4];
__device__ __align__(128) uint32_t g_cand[CR * 512];
__device__ __align__(128) uint32_t g_row[16 * 2 * DM];
__device__ __align__(128) uint32_t g_ypart[NMAIN * NFFN * 4];
__device__ __forceinline__ uint32_t* ypart_slot(int writer, int reader) { return g_ypart + (writer * NMAIN + reader) * 4; }
__device__ uint32_t g_epoch;

__device__ __forceinline__ uint32_t fresh_lane() { uint32_t l; asm volatile("mov.u32 %0, %%laneid;" : "=r"(l)); return l; }
__device__ __forceinline__ uint32_t frag_offset(int warp) {
  const uint32_t l = fresh_lane();
  return ((warp & 3) * 16 + (l & 15)) * 128 + (((l >> 4) ^ (l & 7)) << 4);
}
__device__ __forceinline__ bool elect_one() {
  uint32_t p;
  asm volatile("{ .reg .pred q; elect.sync _|q, 0xffffffff; selp.u32 %0, 1, 0, q; }" : "=r"(p));
  return p;
}
__device__ __forceinline__ uint32_t smem_u32(const void* p) { return (uint32_t)__cvta_generic_to_shared(p); }
__device__ __forceinline__ void mbar_init(uint32_t bar, uint32_t cnt) {
  asm volatile("mbarrier.init.shared::cta.b64 [%0], %1;" ::"r"(bar), "r"(cnt) : "memory");
}
__device__ __forceinline__ void mbar_expect_tx(uint32_t bar, uint32_t bytes) {
  asm volatile("mbarrier.arrive.expect_tx.shared::cta.b64 _, [%0], %1;" ::"r"(bar), "r"(bytes) : "memory");
}
__device__ __forceinline__ void mbar_arrive(uint32_t bar) {
  asm volatile("mbarrier.arrive.shared::cta.b64 _, [%0];" ::"r"(bar) : "memory");
}
__device__ __forceinline__ void mbar_arrive_pred(uint32_t bar, bool p) {
  asm volatile("{ .reg .pred p; setp.ne.b32 p, %1, 0; @p mbarrier.arrive.shared::cta.b64 _, [%0]; }" ::"r"(bar), "r"((int)p) : "memory");
}
__device__ __forceinline__ void mbar_arrive_cl(uint32_t bar, uint32_t off, bool p = true) {
  asm volatile("{ .reg .pred p, q; .reg .b32 a; setp.ne.b32 q, %2, 0; setp.ne.and.b32 p, %0, 0, q; add.u32 a, %0, %1; @p mbarrier.arrive.shared::cluster.b64 _, [a]; }"
               ::"r"(bar), "r"(off), "r"((int)p) : "memory");
}
__device__ __forceinline__ uint32_t mapa(uint32_t addr, uint32_t cta) {
  uint32_t r; asm("mapa.shared::cluster.u32 %0, %1, %2;" : "=r"(r) : "r"(addr), "r"(cta)); return r;
}
__device__ __forceinline__ void cluster_arrive() { asm volatile("barrier.cluster.arrive.relaxed.aligned;" ::: "memory"); }
__device__ __forceinline__ void cluster_wait() { asm volatile("barrier.cluster.wait.aligned;" ::: "memory"); }
__device__ __forceinline__ void watchdog(uint32_t& n) {
}
__device__ __forceinline__ void mbar_wait(uint32_t bar, uint32_t parity) {
  asm volatile("{\n.reg .pred p;\nWAIT_%=:\nmbarrier.try_wait.parity.shared::cta.b64 p, [%0], %1;\n@!p bra WAIT_%=;\n}" ::"r"(bar), "r"(parity) : "memory");
}
__device__ __forceinline__ bool mbar_test(uint32_t bar, uint32_t parity) {
  uint32_t ok;
  asm volatile("{\n.reg .pred p;\nmbarrier.test_wait.parity.shared::cta.b64 p, [%1], %2;\nselp.u32 %0, 1, 0, p;\n}" : "=r"(ok) : "r"(bar), "r"(parity) : "memory");
  return ok;
}
__device__ __forceinline__ uint64_t l2_stream() {
  uint64_t f; asm("createpolicy.fractional.L2::evict_first.b64 %0, 1.0;" : "=l"(f)); return f;
}
__device__ __forceinline__ void tma2d(uint32_t dst, const CUtensorMap* m, int c0, int c1, uint32_t bar) {
  asm volatile("cp.async.bulk.tensor.2d.shared::cluster.global.mbarrier::complete_tx::bytes.L2::cache_hint [%0], [%1, {%3, %4}], [%2], %5;"
               ::"r"(dst), "l"(m), "r"(bar), "r"(c0), "r"(c1), "l"(l2_stream()) : "memory");
}
__device__ __forceinline__ void bulk_load(uint32_t dst, const void* src, uint32_t bytes, uint32_t bar) {
  asm volatile("cp.async.bulk.shared::cluster.global.mbarrier::complete_tx::bytes [%0], [%1], %2, [%3];" ::"r"(dst), "l"(src), "r"(bytes), "r"(bar) : "memory");
}
__device__ __forceinline__ void bulk_load_stream(uint32_t dst, const void* src, uint32_t bytes, uint32_t bar) {
  asm volatile("cp.async.bulk.shared::cluster.global.mbarrier::complete_tx::bytes.L2::cache_hint [%0], [%1], %2, [%3], %4;"
               ::"r"(dst), "l"(src), "r"(bytes), "r"(bar), "l"(l2_stream()) : "memory");
}
__device__ __forceinline__ void tma2d_store(const CUtensorMap* m, uint32_t src, int c0, int c1) {
  asm volatile("cp.async.bulk.tensor.2d.global.shared::cta.bulk_group [%0, {%2, %3}], [%1];" ::"l"(m), "r"(src), "r"(c0), "r"(c1) : "memory");
}
__device__ __forceinline__ void bulk_store(void* dst, uint32_t src, uint32_t bytes) {
  asm volatile("cp.async.bulk.global.shared::cta.bulk_group [%0], [%1], %2;" ::"l"(dst), "r"(src), "r"(bytes) : "memory");
}
__device__ __forceinline__ int slice_of(int i) { return i + ((i & 7) == 1) - ((i & 7) == 2); }
__device__ __forceinline__ uint32_t unit_of(uint32_t table, uint32_t i) { return ((table >> (i * 4)) & 15) * UNIT; }
__device__ __forceinline__ void tma3d(uint32_t dst, const CUtensorMap* m, int c0, int c1, int c2, uint32_t bar) {
  asm volatile("cp.async.bulk.tensor.3d.shared::cluster.global.mbarrier::complete_tx::bytes.L2::cache_hint [%0], [%1, {%3, %4, %5}], [%2], %6;"
               ::"r"(dst), "l"(m), "r"(bar), "r"(c0), "r"(c1), "r"(c2), "l"(l2_stream()) : "memory");
}
template <bool STREAM>
__device__ __forceinline__ void tma3d_mc(uint32_t dst, const CUtensorMap* m, int c0, int c1, int c2, uint32_t bar) {
  if (STREAM)
    asm volatile("cp.async.bulk.tensor.3d.shared::cluster.global.mbarrier::complete_tx::bytes.multicast::cluster.L2::cache_hint [%0], [%1, {%3, %4, %5}], [%2], %6, %7;"
                 ::"r"(dst), "l"(m), "r"(bar), "r"(c0), "r"(c1), "r"(c2), "h"((uint16_t)3), "l"(l2_stream()) : "memory");
  else
    asm volatile("cp.async.bulk.tensor.3d.shared::cluster.global.mbarrier::complete_tx::bytes.multicast::cluster [%0], [%1, {%3, %4, %5}], [%2], %6;"
                 ::"r"(dst), "l"(m), "r"(bar), "r"(c0), "r"(c1), "r"(c2), "h"((uint16_t)3) : "memory");
}
__device__ __forceinline__ void prefetch_map(const CUtensorMap* m) {
  asm volatile("prefetch.tensormap [%0];" ::"l"(m) : "memory");
}
__device__ __forceinline__ void fence_async() { asm volatile("fence.proxy.async.global;" ::: "memory"); }
__device__ __forceinline__ void fence_async_smem() { asm volatile("fence.proxy.async.shared::cta;" ::: "memory"); }
__device__ __forceinline__ void bar_sync(int id, int n) { asm volatile("bar.sync %0, %1;" ::"r"(id), "r"(n) : "memory"); }
__device__ __forceinline__ void bar_arrive(int id, int n) { asm volatile("bar.arrive %0, %1;" ::"r"(id), "r"(n) : "memory"); }
__device__ __forceinline__ void wg_fence() { asm volatile("wgmma.fence.sync.aligned;" ::: "memory"); }
__device__ __forceinline__ void wg_commit() { asm volatile("wgmma.commit_group.sync.aligned;" ::: "memory"); }
template <int N> __device__ __forceinline__ void wg_wait() { asm volatile("wgmma.wait_group.sync.aligned %0;" ::"n"(N) : "memory"); }
__device__ __forceinline__ uint64_t make_desc(uint32_t addr, uint32_t lbo, uint32_t sbo) {
  return (uint64_t)((addr & 0x3FFFF) >> 4) | ((uint64_t)(lbo >> 4) << 16) | ((uint64_t)(sbo >> 4) << 32) | (1ull << 62);
}
__device__ __forceinline__ uint32_t ld_relaxed(const uint32_t* p) {
  uint32_t v; asm volatile("ld.relaxed.gpu.global.u32 %0, [%1];" : "=r"(v) : "l"(p) : "memory"); return v;
}
__device__ __forceinline__ uint32_t ld_acquire(const uint32_t* p) {
  uint32_t v; asm volatile("ld.acquire.gpu.global.u32 %0, [%1];" : "=r"(v) : "l"(p) : "memory"); return v;
}
__device__ __forceinline__ uint4 ld_relaxed4(const uint32_t* p) {
  uint4 v; asm volatile("ld.relaxed.gpu.global.v4.u32 {%0,%1,%2,%3}, [%4];" : "=r"(v.x), "=r"(v.y), "=r"(v.z), "=r"(v.w) : "l"(p) : "memory"); return v;
}
__device__ __forceinline__ void st_relaxed(uint32_t* p, uint32_t v) {
  asm volatile("st.relaxed.gpu.global.u32 [%0], %1;" ::"l"(p), "r"(v) : "memory");
}
__device__ __forceinline__ void st_relaxed4(uint32_t* p, uint32_t a, uint32_t b, uint32_t c, uint32_t d) {
  asm volatile("st.relaxed.gpu.global.v4.u32 [%0], {%1,%2,%3,%4};" ::"l"(p), "r"(a), "r"(b), "r"(c), "r"(d) : "memory");
}
__device__ __forceinline__ void st_b128(uint32_t* p, uint32_t a, uint32_t b, uint32_t c, uint32_t d) {
  asm volatile("{ .reg .b64 u, v; .reg .b128 w; mov.b64 u, {%1, %2}; mov.b64 v, {%3, %4}; mov.b128 w, {u, v}; st.relaxed.gpu.global.b128 [%0], w; }"
               ::"l"(p), "r"(a), "r"(b), "r"(c), "r"(d) : "memory");
}
__device__ __forceinline__ uint4 ld_b128(const uint32_t* p) {
  uint4 r;
  asm volatile("{ .reg .b64 u, v; .reg .b128 w; ld.relaxed.gpu.global.b128 w, [%4]; mov.b128 {u, v}, w; mov.b64 {%0, %1}, u; mov.b64 {%2, %3}, v; }"
               : "=r"(r.x), "=r"(r.y), "=r"(r.z), "=r"(r.w) : "l"(p) : "memory");
  return r;
}
__device__ __forceinline__ void st_pairs(uint32_t* p, uint32_t a, uint32_t b, uint32_t tag) {
  asm volatile("{ .reg .b64 u, v; mov.b64 u, {%1, %3}; mov.b64 v, {%2, %3}; st.relaxed.gpu.global.v2.b64 [%0], {u, v}; }"
               ::"l"(p), "r"(a), "r"(b), "r"(tag) : "memory");
}
__device__ __forceinline__ uint4 ld_pairs(const uint32_t* p) {
  uint4 v;
  asm volatile("{ .reg .b64 u, v; ld.relaxed.gpu.global.v2.b64 {u, v}, [%4]; mov.b64 {%0, %1}, u; mov.b64 {%2, %3}, v; }"
               : "=r"(v.x), "=r"(v.y), "=r"(v.z), "=r"(v.w) : "l"(p) : "memory");
  return v;
}
__device__ __forceinline__ uint2 ld_pair(const uint32_t* p) {
  uint2 v;
  asm volatile("{ .reg .b64 u; ld.relaxed.gpu.global.b64 u, [%2]; mov.b64 {%0, %1}, u; }" : "=r"(v.x), "=r"(v.y) : "l"(p) : "memory");
  return v;
}
__device__ __forceinline__ void red_release(uint32_t* p, uint32_t v) {
  asm volatile("red.release.gpu.global.add.u32 [%0], %1;" ::"l"(p), "r"(v) : "memory");
}
__device__ __forceinline__ uint32_t ldg_nc1(const void* p) {
  uint32_t v;
  asm volatile("ld.global.nc.u32 %0, [%1];" : "=r"(v) : "l"(p));
  return v;
}
__device__ __forceinline__ uint4 ldg_nc4(const void* p) {
  uint4 v; asm volatile("ld.global.nc.L1::no_allocate.v4.u32 {%0,%1,%2,%3}, [%4];" : "=r"(v.x), "=r"(v.y), "=r"(v.z), "=r"(v.w) : "l"(p)); return v;
}
__device__ __forceinline__ uint4 ldg_stream4(const void* p) {
  uint4 v;
  asm volatile("ld.global.nc.L1::no_allocate.L2::cache_hint.v4.u32 {%0,%1,%2,%3}, [%4], %5;" : "=r"(v.x), "=r"(v.y), "=r"(v.z), "=r"(v.w) : "l"(p), "l"(l2_stream()));
  return v;
}
__device__ __forceinline__ void stg4(void* p, uint4 v) {
  asm volatile("st.global.v4.u32 [%0], {%1,%2,%3,%4};" ::"l"(p), "r"(v.x), "r"(v.y), "r"(v.z), "r"(v.w) : "memory");
}
__device__ __forceinline__ void wait_counter(const uint32_t* p, uint32_t target) {
  uint32_t n = 0;
  while (__any_sync(0xffffffffu, (int)(ld_acquire(p) - target) < 0)) { watchdog(n); }
}
__device__ __forceinline__ uint32_t tagf(float v, uint32_t tag) { return (__float_as_uint(v) & ~3u) | tag; }
__device__ __forceinline__ bool tag_ok(uint4 v, uint32_t tag) { return (((v.x ^ tag) | (v.y ^ tag) | (v.z ^ tag) | (v.w ^ tag)) & 3u) == 0; }
__device__ __forceinline__ float untag_sum(uint32_t a, uint32_t b) { return __uint_as_float(a & ~3u) + __uint_as_float(b & ~3u); }
__device__ __forceinline__ uint4 poll4(const uint32_t* p, uint32_t tag) {
  uint4 v = ld_relaxed4(p);
  uint32_t n = 0;
  while (!__all_sync(0xffffffffu, tag_ok(v, tag))) { v = ld_relaxed4(p); watchdog(n); }
  return v;
}
__device__ __forceinline__ float bf_lo(uint32_t v) { return __uint_as_float(v << 16); }
__device__ __forceinline__ float bf_hi(uint32_t v) { return __uint_as_float(v & 0xffff0000u); }
__device__ __forceinline__ uint32_t pack_bf(float lo, float hi) {
  uint32_t r; asm("cvt.rn.bf16x2.f32 %0, %1, %2;" : "=r"(r) : "f"(hi), "f"(lo)); return r;
}
__device__ __forceinline__ float rbf(float v) { return __uint_as_float(pack_bf(0.f, v) & 0xffff0000u); }
__device__ __forceinline__ uint32_t hmul2(uint32_t a, uint32_t b) {
  uint32_t r; asm("mul.rn.bf16x2 %0, %1, %2;" : "=r"(r) : "r"(a), "r"(b)); return r;
}
__device__ __forceinline__ uint32_t hadd2(uint32_t a, uint32_t b) {
  uint32_t r; asm("add.rn.bf16x2 %0, %1, %2;" : "=r"(r) : "r"(a), "r"(b)); return r;
}
__device__ __forceinline__ uint32_t hsub2(uint32_t a, uint32_t b) {
  uint32_t r; asm("sub.rn.bf16x2 %0, %1, %2;" : "=r"(r) : "r"(a), "r"(b)); return r;
}
__device__ __forceinline__ float rcp(float x) { float r; asm("rcp.approx.ftz.f32 %0, %1;" : "=f"(r) : "f"(x)); return r; }
__device__ __forceinline__ float ex2(float x) { float r; asm("ex2.approx.ftz.f32 %0, %1;" : "=f"(r) : "f"(x)); return r; }
__device__ __forceinline__ void stmatrix4(uint32_t addr, uint32_t a, uint32_t b, uint32_t c, uint32_t d) {
  asm volatile("stmatrix.sync.aligned.m8n8.x4.shared.b16 [%0], {%1,%2,%3,%4};" ::"r"(addr), "r"(a), "r"(b), "r"(c), "r"(d) : "memory");
}
__device__ __forceinline__ void ldmatrix4(uint32_t addr, uint32_t& a, uint32_t& b, uint32_t& c, uint32_t& d) {
  asm volatile("ldmatrix.sync.aligned.m8n8.x4.shared.b16 {%0,%1,%2,%3}, [%4];" : "=r"(a), "=r"(b), "=r"(c), "=r"(d) : "r"(addr) : "memory");
}
__device__ __forceinline__ void ldmatrix4t(uint32_t addr, uint32_t& a, uint32_t& b, uint32_t& c, uint32_t& d) {
  asm volatile("ldmatrix.sync.aligned.m8n8.x4.trans.shared.b16 {%0,%1,%2,%3}, [%4];" : "=r"(a), "=r"(b), "=r"(c), "=r"(d) : "r"(addr) : "memory");
}
__device__ __forceinline__ void mma16816(float (&d)[4], uint32_t a0, uint32_t a1, uint32_t a2, uint32_t a3, uint32_t b0, uint32_t b1) {
  asm volatile("mma.sync.aligned.m16n8k16.row.col.f32.bf16.bf16.f32 {%0,%1,%2,%3}, {%4,%5,%6,%7}, {%8,%9}, {%0,%1,%2,%3};"
               : "+f"(d[0]), "+f"(d[1]), "+f"(d[2]), "+f"(d[3]) : "r"(a0), "r"(a1), "r"(a2), "r"(a3), "r"(b0), "r"(b1));
}
__device__ __forceinline__ void sts1(uint32_t a, uint32_t v) { asm volatile("st.shared.u32 [%0], %1;" ::"r"(a), "r"(v) : "memory"); }
__device__ __forceinline__ uint4 lds4(uint32_t a) {
  uint4 v; asm volatile("ld.shared.v4.u32 {%0,%1,%2,%3}, [%4];" : "=r"(v.x), "=r"(v.y), "=r"(v.z), "=r"(v.w) : "r"(a) : "memory"); return v;
}
__device__ __forceinline__ uint2 lds2(uint32_t a) {
  uint2 v; asm volatile("ld.shared.v2.u32 {%0,%1}, [%2];" : "=r"(v.x), "=r"(v.y) : "r"(a) : "memory"); return v;
}
__device__ __forceinline__ uint32_t lds1(uint32_t a) {
  uint32_t v; asm volatile("ld.shared.u32 %0, [%1];" : "=r"(v) : "r"(a) : "memory"); return v;
}
__device__ __forceinline__ void sts2(uint32_t a, uint32_t x, uint32_t y) { asm volatile("st.shared.v2.u32 [%0], {%1,%2};" ::"r"(a), "r"(x), "r"(y) : "memory"); }
__device__ __forceinline__ void sts4(uint32_t a, uint4 v) {
  asm volatile("st.shared.v4.u32 [%0], {%1,%2,%3,%4};" ::"r"(a), "r"(v.x), "r"(v.y), "r"(v.z), "r"(v.w) : "memory");
}
__device__ __forceinline__ float silu_f(float v) { return __fdividef(v, 1.f + __expf(-v)); }
__device__ __forceinline__ uint32_t hfma2(uint32_t a, uint32_t b, uint32_t c) {
  uint32_t r; asm("fma.rn.bf16x2 %0, %1, %2, %3;" : "=r"(r) : "r"(a), "r"(b), "r"(c)); return r;
}
__device__ __forceinline__ void split_inv(float sd, uint32_t& ih, uint32_t& il) {
  const float inv = rcp(sd);
  ih = pack_bf(inv, inv);
  const float lo = inv - bf_lo(ih);
  il = pack_bf(lo, lo);
}
__device__ __forceinline__ uint32_t ln_norm(uint32_t x, uint32_t mean2, uint32_t ih, uint32_t il) {
  const uint32_t d = hsub2(x, mean2);
  return hfma2(d, ih, hmul2(d, il));
}
__device__ __forceinline__ uint32_t ln_mod(uint32_t x, uint32_t mean2, uint32_t ih, uint32_t il, uint32_t c1, uint32_t sh) {
  return hadd2(hmul2(ln_norm(x, mean2, ih, il), c1), sh);
}

#define R8(a, i) "+f"(a[i]), "+f"(a[i + 1]), "+f"(a[i + 2]), "+f"(a[i + 3]), "+f"(a[i + 4]), "+f"(a[i + 5]), "+f"(a[i + 6]), "+f"(a[i + 7])
#define D64 "{%0,%1,%2,%3,%4,%5,%6,%7,%8,%9,%10,%11,%12,%13,%14,%15,%16,%17,%18,%19,%20,%21,%22,%23,%24,%25,%26,%27,%28,%29,%30,%31," \
            "%32,%33,%34,%35,%36,%37,%38,%39,%40,%41,%42,%43,%44,%45,%46,%47,%48,%49,%50,%51,%52,%53,%54,%55,%56,%57,%58,%59,%60,%61,%62,%63}"
template <int TB>
__device__ __forceinline__ void mma_ss(float (&d)[64], uint64_t da, uint64_t db, int sc) {
  asm volatile("{\n.reg .pred p;\nsetp.ne.b32 p, %66, 0;\n"
               "wgmma.mma_async.sync.aligned.m64n128k16.f32.bf16.bf16 " D64 ", %64, %65, p, 1, 1, 0, %67;\n}"
               : R8(d, 0), R8(d, 8), R8(d, 16), R8(d, 24), R8(d, 32), R8(d, 40), R8(d, 48), R8(d, 56)
               : "l"(da), "l"(db), "r"(sc), "n"(TB));
}
template <int TB>
__device__ __forceinline__ void mma_rs(float (&d)[64], uint32_t a0, uint32_t a1, uint32_t a2, uint32_t a3, uint64_t db, int sc) {
  asm volatile("{\n.reg .pred p;\nsetp.ne.b32 p, %69, 0;\n"
               "wgmma.mma_async.sync.aligned.m64n128k16.f32.bf16.bf16 " D64 ", {%64,%65,%66,%67}, %68, p, 1, 1, %70;\n}"
               : R8(d, 0), R8(d, 8), R8(d, 16), R8(d, 24), R8(d, 32), R8(d, 40), R8(d, 48), R8(d, 56)
               : "r"(a0), "r"(a1), "r"(a2), "r"(a3), "l"(db), "r"(sc), "n"(TB));
}
#define D128 "{%0,%1,%2,%3,%4,%5,%6,%7,%8,%9,%10,%11,%12,%13,%14,%15,%16,%17,%18,%19,%20,%21,%22,%23,%24,%25,%26,%27,%28,%29,%30,%31," \
             "%32,%33,%34,%35,%36,%37,%38,%39,%40,%41,%42,%43,%44,%45,%46,%47,%48,%49,%50,%51,%52,%53,%54,%55,%56,%57,%58,%59,%60,%61,%62,%63," \
             "%64,%65,%66,%67,%68,%69,%70,%71,%72,%73,%74,%75,%76,%77,%78,%79,%80,%81,%82,%83,%84,%85,%86,%87,%88,%89,%90,%91,%92,%93,%94,%95," \
             "%96,%97,%98,%99,%100,%101,%102,%103,%104,%105,%106,%107,%108,%109,%110,%111,%112,%113,%114,%115,%116,%117,%118,%119,%120,%121,%122,%123,%124,%125,%126,%127}"
#define R128(d, e) R8(d, 0), R8(d, 8), R8(d, 16), R8(d, 24), R8(d, 32), R8(d, 40), R8(d, 48), R8(d, 56), \
                   R8(e, 0), R8(e, 8), R8(e, 16), R8(e, 24), R8(e, 32), R8(e, 40), R8(e, 48), R8(e, 56)
__device__ __forceinline__ void mma256_ss(float (&d)[64], float (&e)[64], uint64_t da, uint64_t db, int sc) {
  asm volatile("{\n.reg .pred p;\nsetp.ne.b32 p, %130, 0;\n"
               "wgmma.mma_async.sync.aligned.m64n256k16.f32.bf16.bf16 " D128 ", %128, %129, p, 1, 1, 0, 1;\n}"
               : R128(d, e) : "l"(da), "l"(db), "r"(sc));
}
__device__ __forceinline__ void mma256_rs(float (&d)[64], float (&e)[64], uint32_t a0, uint32_t a1, uint32_t a2, uint32_t a3, uint64_t db) {
  asm volatile("{\n.reg .pred p;\nsetp.ne.b32 p, 1, 0;\n"
               "wgmma.mma_async.sync.aligned.m64n256k16.f32.bf16.bf16 " D128 ", {%128,%129,%130,%131}, %132, p, 1, 1, 1;\n}"
               : R128(d, e) : "r"(a0), "r"(a1), "r"(a2), "r"(a3), "l"(db));
}
template <int N> __device__ __forceinline__ void keep(float (&a)[N]) {
#pragma unroll
  for (int i = 0; i < N; i++) asm volatile("" : "+f"(a[i])::"memory");
}
template <int N> __device__ __forceinline__ void keep(uint32_t (&a)[N]) {
#pragma unroll
  for (int i = 0; i < N; i++) asm volatile("" : "+r"(a[i])::"memory");
}

#define STAMP(idx) do {} while (0)
#define PROF(grp, cond, idx) do {} while (0)

constexpr float SCL2 = 1.4426950408889634f * 0.08838834764831845f;

__device__ __forceinline__ void pack_p(const float (&s)[64], uint32_t (&p)[32]) {
#pragma unroll
  for (int i = 0; i < 32; i++) p[i] = pack_bf(s[2 * i], s[2 * i + 1]);
}

__device__ __forceinline__ void issue_qk(float (&s)[64], uint32_t q0, uint32_t q1, uint32_t kslot) {
  const uint64_t db = make_desc(kslot, 16, 1024), da0 = make_desc(q0, 16, 1024), da1 = make_desc(q1, 16, 1024);
#pragma unroll
  for (int kk = 0; kk < 8; kk++) mma_ss<0>(s, (kk < 4 ? da0 : da1) + (kk & 3) * 2, db + (kk >> 2) * 1024 + (kk & 3) * 2, kk != 0);
}
__device__ __forceinline__ void issue_pv(float (&o)[64], uint32_t (&p)[32], uint32_t vslot, int acc) {
  uint64_t db = make_desc(vslot, 16384, 1024);
#pragma unroll
  for (int kk = 0; kk < 8; kk++)
    mma_rs<1>(o, p[4 * kk], p[4 * kk + 1], p[4 * kk + 2], p[4 * kk + 3], db + kk * 128, kk == 0 ? acc : 1);
}

template <int H>
__device__ __forceinline__ void store_chunk(const float (&a)[64], uint32_t addr) {
#pragma unroll
  for (int i = 8 * H; i < 8 * H + 8; i += 2)
    stmatrix4(addr ^ ((i & 7) << 4), pack_bf(a[4 * i], a[4 * i + 1]), pack_bf(a[4 * i + 2], a[4 * i + 3]),
              pack_bf(a[4 * i + 4], a[4 * i + 5]), pack_bf(a[4 * i + 6], a[4 * i + 7]));
}
template <int H>
__device__ __forceinline__ void store_chunk(const float (&a)[64], float i0, float i1, uint32_t addr) {
#pragma unroll
  for (int i = 8 * H; i < 8 * H + 8; i += 2)
    stmatrix4(addr ^ ((i & 7) << 4), pack_bf(a[4 * i] * i0, a[4 * i + 1] * i0), pack_bf(a[4 * i + 2] * i1, a[4 * i + 3] * i1),
              pack_bf(a[4 * i + 4] * i0, a[4 * i + 5] * i0), pack_bf(a[4 * i + 6] * i1, a[4 * i + 7] * i1));
}
__device__ __forceinline__ float inv_quad_sum(float l) {
  l += __shfl_xor_sync(0xffffffffu, l, 1);
  l += __shfl_xor_sync(0xffffffffu, l, 2);
  return rcp(l);
}

__device__ __forceinline__ void write_table(uint32_t table, bool ca, uint32_t t, const uint4& m0, const uint4& m1) {
  float c0 = untag_sum(m0.x, m1.x), c1 = untag_sum(m0.y, m1.y), c2 = untag_sum(m0.z, m1.z), c3 = untag_sum(m0.w, m1.w);
  if (ca) { c0 = 1.f + rbf(c0); c1 = 1.f + rbf(c1); c2 = 1.f + rbf(c2); c3 = 1.f + rbf(c3); }
  const uint32_t d = table + (t >> 2) * 64 + (t & 1) * 32 + (t & 2) * 2 + (ca ? 0 : 8);
  sts1(d, pack_bf(c0, c1));
  sts1(d + 16, pack_bf(c2, c3));
}

__device__ __forceinline__ void ln_scalars(float mean, float var, float& mb, float& sd) {
  mb = rbf(mean);
  float r; asm("sqrt.approx.ftz.f32 %0, %1;" : "=f"(r) : "f"(rbf(rbf(var) + 1e-5f)));
  sd = rbf(r);
}

__global__ void __cluster_dims__(2, 1, 1) __launch_bounds__(384, 1) fused_kernel(const __grid_constant__ Maps maps, const Ptrs P) {
  extern __shared__ __align__(1024) uint8_t smem_raw[];
  const uint32_t base = smem_u32(smem_raw);
  const int tid = threadIdx.x, lane = tid & 31;
  const int warp = __shfl_sync(0xffffffffu, tid >> 5, 0);
  const int b = blockIdx.x;
  PROF(31, tid == 0, 0);

  if (b >= NMAIN) {
    float* sc = reinterpret_cast<float*>(smem_raw);
    float* red = sc + DM;
    for (int k = tid; k < DM; k += 384) sc[k] = rbf(silu_f(__bfloat162float(P.c[k])));
    __syncthreads();
    if (tid < 256) {
      const int col = 2048 + (b - NMAIN) * 1024 + (tid & 127) * 8, r0 = (tid >> 7) * 512;
      float acc[8];
#pragma unroll
      for (int e = 0; e < 8; e++) acc[e] = 0.f;
#pragma unroll 1
      for (int r = r0; r < r0 + 512; r += HU) {
        uint4 w[HU];
#pragma unroll
        for (int u = 0; u < HU; u++) w[u] = ldg_stream4(P.w_mod + (size_t)(r + u) * NMOD + col);
#pragma unroll
        for (int u = 0; u < HU; u++) {
          float s = sc[r + u];
          acc[0] += s * bf_lo(w[u].x); acc[1] += s * bf_hi(w[u].x); acc[2] += s * bf_lo(w[u].y); acc[3] += s * bf_hi(w[u].y);
          acc[4] += s * bf_lo(w[u].z); acc[5] += s * bf_hi(w[u].z); acc[6] += s * bf_lo(w[u].w); acc[7] += s * bf_hi(w[u].w);
        }
      }
      if (tid >= 128) {
#pragma unroll
        for (int e = 0; e < 8; e++) red[(tid & 127) * 8 + e] = acc[e];
      }
      const uint32_t tag = ld_relaxed(&g_epoch) % 3 + 1;
      bar_sync(1, 256);
      if (tid < 128) {
        uint32_t o[8];
#pragma unroll
        for (int e = 0; e < 8; e++) o[e] = __float_as_uint(rbf(acc[e] + red[tid * 8 + e])) | tag;
        st_relaxed4(g_mod + col, o[0], o[1], o[2], o[3]);
        st_relaxed4(g_mod + col + 4, o[4], o[5], o[6], o[7]);
        const uint4 wr = ldg_nc4(P.w_r + tid * 8);
        const uint32_t wv[4] = {wr.x, wr.y, wr.z, wr.w};
        float dsum = 0.f;
#pragma unroll
        for (int e = 0; e < 8; e++) {
          const float m = bf_hi(o[e]);
          dsum += (b == NMAIN + 2 ? rbf(1.f + m) : m) * ((e & 1) ? bf_hi(wv[e >> 1]) : bf_lo(wv[e >> 1]));
        }
#pragma unroll
        for (int k = 16; k > 0; k >>= 1) dsum += __shfl_xor_sync(0xffffffffu, dsum, k);
        if (lane == 0) st_relaxed(g_mod + (b - NMAIN) * 4 + warp, tagf(dsum, tag));
      }
    }
    PROF(2, tid == 0, 1);
    return;
  }

  const int rank = b & 1;
  const int rb = ((b >> 4) << 1) | rank, cj = (b >> 1) & 7;
  const bool late = b & 4;
  const uint32_t bfull = base + OFF_BAR, bempty = bfull + NSLOT * 8;
  const uint32_t gfull = bempty + NSLOT * 8, gempty = gfull + 32;
  const uint32_t bar_ofull = gempty + 32;
  const uint32_t bar_ofree = bar_ofull + 32;
  const uint32_t bar_par = bar_ofree + 32;
  const uint32_t bar_mod = bar_par + 8;
  const uint32_t bar_pread = bar_mod + 8;
  const uint32_t bar_xres = bar_pread + 8;
  const uint32_t bar_ring = bar_xres + 8;
  const uint32_t bar_box = bar_ring + 24;
  const uint32_t bar_go = bar_box + 96;
  const uint32_t bar_go2 = bar_go + 16;
  const uint32_t bar_cnt = bar_go + 24;
  const uint32_t xfull = bar_go + 40, xempty = xfull + 32;
  const uint32_t bar_hw = xempty + 32, bar_hx = bar_hw + 8;
  const uint32_t bar_hpub = bar_hx + 16;
  const uint32_t bar_win = bar_hpub + 16;
  const uint32_t bar_rx = bar_win + 8;
  const uint32_t bar_sel = bar_rx + 8;
  const uint32_t bar_gate = bar_sel + 8;
  const uint32_t bar_rel = bar_gate + 8;
  const uint32_t bar_od = bar_rel + 8;
  const uint32_t bar_mod2 = bar_od + 8;
  const uint32_t bar_res = bar_go + 8;
  const uint32_t stage = base + OFF_STAGE, par = base + OFF_PAR;

  if (warp == 10 && elect_one()) prefetch_map(&maps.wm);
  if (warp == 8 && elect_one()) {
    for (int s = 0; s < NSLOT; s++) { mbar_init(bfull + s * 8, 1); mbar_init(bempty + s * 8, 16); }
    for (int s = 0; s < 4; s++) { mbar_init(gfull + s * 8, 1); mbar_init(gempty + s * 8, 16); mbar_init(xfull + s * 8, 1); mbar_init(xempty + s * 8, 8); mbar_init(bar_ofree + s * 8, 1); mbar_init(bar_ofull + s * 8, 128); }
    mbar_init(bar_par, 64); mbar_init(bar_mod, 256); mbar_init(bar_pread, 2); mbar_init(bar_xres, 1);
    mbar_init(bar_ring, 8); mbar_init(bar_ring + 8, 8); mbar_init(bar_ring + 16, 8);
    mbar_init(bar_go, 1); mbar_init(bar_go2, 1); mbar_init(bar_cnt, 1); mbar_init(bar_cnt + 8, 1); mbar_init(bar_hpub, 8); mbar_init(bar_hpub + 8, 8); mbar_init(bar_res, 1); mbar_init(bar_win, 1); mbar_init(bar_rx, 1); mbar_init(bar_sel, 64); mbar_init(bar_gate, 8); mbar_init(bar_rel, 8); mbar_init(bar_od, 1); mbar_init(bar_mod2, 64);
    for (int s = 0; s < 12; s++) mbar_init(bar_box + s * 8, 1);
    asm volatile("fence.mbarrier_init.release.cluster;" ::: "memory");
    prefetch_map(&maps.x); prefetch_map(&maps.wq); prefetch_map(&maps.k); prefetch_map(&maps.v);
  }
  if (warp == 9 && elect_one()) {
    mbar_init(bar_hw, 1); mbar_init(bar_hx, 1); mbar_init(bar_hx + 8, 1);
    asm volatile("fence.mbarrier_init.release.cluster;" ::: "memory");
    mbar_expect_tx(bar_hw, 32768);
    mbar_expect_tx(bar_hx, 16384);
    mbar_expect_tx(bar_hx + 8, 16384);
    const __nv_bfloat16* xs = P.x + (size_t)(rb * 128 + cj * 16) * DM;
    bulk_load(base + 2 * GST_BYTES, xs, 16384, bar_hx);
    if (!late) {
      tma2d(stage, &maps.wm, (b >> 1) * 32, rank * 512, bar_hw);
      tma2d(stage + 16384, &maps.wm, (b >> 1) * 32, rank * 512 + 256, bar_hw);
    }
    bulk_load(base + 3 * GST_BYTES, xs + 8 * DM, 16384, bar_hx + 8);
  }
  cluster_arrive();

  if (warp >= 8) {
    asm volatile("setmaxnreg.dec.sync.aligned.u32 40;");
    if (warp < 10) bar_arrive(1, 320);
    const uint32_t epoch = ld_relaxed(&g_epoch);
    cluster_wait();
    if (warp == 8) {
      const int kvrow = (cj >> 1) * SK + (SK - WIN);
      int wch = cj * 8 + rank * 2;
#pragma unroll 1
      for (int ps = 0; ps < 3; ps++) {
        const CUtensorMap* mw = ps == 2 ? &maps.wo : &maps.wq;
        const uint32_t xt = ps == 1 ? XT1 : XT2, wt = ps == 0 ? WT0 : (ps == 1 ? WT1 : WT2);
        const int nst = ps == 2 ? 32 : 16;
#pragma unroll 1
        for (int i = 0; i < nst; i++) {
          const uint32_t bf = gfull + (i & 3) * 8;
          const int kt = ps == 2 ? (((cj & 1) * 4 + ((i >> 1) & 3)) * 4 + (i >> 3)) * 2 + (i & 1) : (ps ? i : slice_of(i) + (b & 14)) & 15;
          const uint32_t wd = base + unit_of(wt, i & 3) + rank * UNIT, xd = base + unit_of(xt, i & 3);
          const uint8_t* xs = g_act + (uint32_t)(rb * 80 + (ps - 1) * 16 + kt) * UNIT;
          if (ps == 0 && i == HD) mbar_wait(bar_mod, 0);
          const bool xfirst = ps && i < 2;
          if (ps == 2 && i == 0) mbar_wait(bar_ofree + 24, 0);
          if (i == 0) fence_async();
          mbar_wait(gempty + (i & 3) * 8, ((i >> 2) & 1) ^ 1);
          if (elect_one()) {
            mbar_expect_tx(bf, ps ? GST_BYTES : 2 * UNIT);
            if (xfirst) bulk_load_stream(xd, xs, UNIT, bf);
          }
          if (ps && i < 4) mbar_wait(bempty + i * 8, 1);
          if (elect_one()) tma3d_mc<true>(wd, mw, 0, (i == 31 ? kt ^ (rank * 32) : kt) * 64, i == 31 ? cj * 2 : wch, bf);
          if (ps) {
            if (i == 16 || i == 24) { mbar_wait(bar_cnt + i - 16, 0); fence_async(); }
            if (i == RES0) mbar_wait(bar_res, 0);
            if (i == 2) mbar_wait(bar_ofree + (ps - 1) * 16, 0);
            if (elect_one()) {
              if (i == 31) bulk_load(xd, xs, UNIT, bf); else if (!xfirst) bulk_load_stream(xd, xs, UNIT, bf);
              mbar_arrive_pred(bar_go, i == GOST - 1);
              mbar_arrive_pred(bar_go2, ps == 1 && i == PG0);
              mbar_arrive_pred(bar_od, i == (ps == 1 ? ODS1 : ODS));
              if (i == RES0) mbar_expect_tx(bar_xres, 32768);
              if (i == RES0 || i == RES1) tma2d(base + OFF_RES + (i == RES1) * UNIT, &maps.x, cj * 128 + (i == RES1) * 64, rb * 128, bar_xres);
            }
          }
        }
        if (ps == 2) break;
        wch = ps ? ((wch >> 3) ^ rank) * 2 : wch + 4;
#pragma unroll 1
        for (int u = 0; u < 16; u++) {
          const bool isk = (u == 0) || ((u & 1) && u < 15);
          const int blk = (isk ? (u + 1) >> 1 : (u == 15 ? 7 : (u >> 1) - 1)) & 3;
          const uint32_t sl = base + unit_of(ps ? AT1 : AT0, u & 3) + rank * UNIT, bf = bfull + (u & 3) * 8;
          if (u < 4) mbar_wait(gempty + ((u + 1) >> 1) * 8, 1);
          mbar_wait(bempty + (u & 3) * 8, ((u >> 2) & 1) ^ 1);
          if (elect_one()) {
            mbar_expect_tx(bf, SLOT_BYTES);
            if (ps && u >= 7 && u != 8) tma3d_mc<true>(sl, isk ? &maps.k : &maps.v, 0, kvrow + blk * 128, rank, bf);
            else tma3d_mc<false>(sl, isk ? &maps.k : &maps.v, 0, kvrow + blk * 128, rank, bf);
          }
        }
      }
      if (elect_one()) mbar_expect_tx(bar_rx, UNIT);
      mbar_wait(bar_rel, 0);
      if (elect_one()) {
        bulk_load_stream(base + UNIT, g_act + (uint32_t)(rb * 80 + 16 + 63 - (cj & 1) * 32) * UNIT, UNIT, bar_rx);
      }
      if (b < NFFN) {
#pragma unroll 1
        for (int u = 0; u < 12; u++) {
          const uint32_t dst = base + unit_of(u < 4 ? FT_G : (u < 8 ? FT_U : FT_D), u & 3);
          if (elect_one()) mbar_expect_tx(bar_box + u * 8, UNIT);
          if (u == 0 || u == 2 || u == 8) mbar_wait(bar_ring + (u == 8 ? 16 : u * 4), 0);
          const int fp = u < 8 ? FPACE0 : FPACE;
          if (u >= fp) mbar_wait(bar_box + (u - fp) * 8, 0);
          if (elect_one()) {
            if (u < 8) tma2d(dst, u < 4 ? &maps.wg : &maps.wu, b * 32, (u & 3) * 256, bar_box + u * 8);
            else tma3d(dst, &maps.wd, 0, b * 32, (u - 8) * 4, bar_box + u * 8);
          }
        }
      }
    } else if (warp == 9) {
      const uint32_t target = 8 * (epoch + 1);
      uint32_t hmask = 0;
#pragma unroll 1
      for (int i = 0; i < 16; i++) {
        if (i == HDX) mbar_wait(bar_mod, 0);
        const int kt = (2 * cj + slice_of(i)) & 15;
        const uint32_t need = i == 15 ? 0xffffu : 1u << kt;
        if (i >= NRS && (hmask & need) != need) {
          uint32_t n = 0;
          do { hmask = __ballot_sync(0xffffffffu, ld_acquire(&g_cnt_h[rb * 32 + (lane & 15)]) == epoch + 1); watchdog(n); } while ((hmask & need) != need);
          PROF(1, lane == 0 && i == NRS, 26);
          fence_async();
        }
        mbar_wait(xempty + (i & 3) * 8, ((i >> 2) & 1) ^ 1);
        if (elect_one()) {
          mbar_expect_tx(xfull + (i & 3) * 8, UNIT);
          if (i < NRS) tma2d(base + (i & 3) * GST_BYTES, &maps.x, kt * 64, rb * 128, xfull + (i & 3) * 8);
          else bulk_load_stream(base + (i & 3) * GST_BYTES, g_act + (uint32_t)(rb * 80 + kt) * UNIT, UNIT, xfull + (i & 3) * 8);
        }
      }
      prefetch_map(&maps.wo);
#pragma unroll 1
      for (int t = 0; t < 4; t++) {
        if (t & 1) mbar_wait(bar_od, t >> 1);
#pragma unroll 1
        for (int p = 0; p < 32768 / OPS; p++) {
          const uint32_t w = p / (16384 / OPS), c = (p / (8192 / OPS)) & 1, off = w * 8192 + (p % (8192 / OPS)) * OPS;
          mbar_wait(bar_ofull + (t & 1) * 16 + w * 8, t >> 1);
          if (elect_one()) {
            bulk_store(g_act + (uint32_t)(rb * 80 + 16 + (cj * 4 + t) * 2 + c) * UNIT + off, base + unit_of(QT, 2 * t + c) + off, OPS);
            asm volatile("cp.async.bulk.commit_group;" ::: "memory");
            asm volatile("cp.async.bulk.wait_group.read 0;" ::: "memory");
          }
        }
        if (elect_one()) {
          mbar_arrive(t < 3 ? bar_ofree + t * 8 : bar_res);
          asm volatile("cp.async.bulk.wait_group 0;" ::: "memory");
          fence_async();
          red_release(&g_cnt_o[((rb * 4 + t) * 2 + (cj >> 2)) * 32], 2);
        }
        if (t) {
          wait_counter(&g_cnt_o[(rb * 8 + 2 * t + (cj & 1)) * 32], target);
          if (t & 1) wait_counter(&g_cnt_o[(rb * 8 + (t == 1 ? cj & 1 : 7 - (cj & 1))) * 32], target);
          if (elect_one()) mbar_arrive(t == 1 ? bar_ofree + 24 : bar_cnt + t * 8 - 16);
        }
      }
      PROF(2, lane == 0, 27);
      const uint32_t tag = epoch % 3 + 1;
      const uint32_t* inbox = g_cand + (b >> 1) % CR * 512 + (lane & 15) * CS;
      mbar_wait(bar_ring + 16, 0);
      uint32_t c0 = ld_relaxed(inbox), n = 0;
#define CAND_STEP(cv)                                                                                        \
      {                                                                                                      \
        const bool valid = (cv & 3u) == tag, all = __all_sync(0xffffffffu, valid);                           \
        const uint32_t best = __reduce_max_sync(0xffffffffu, valid ? cv : 0u);                               \
        const uint32_t blk = __ffs(__ballot_sync(0xffffffffu, cv == best)) - 1;                              \
        if (best) sts2(par + PAR_CONST + 56, best, (blk << 7 | (~best >> 2 & 127)) | (all ? 0x1800 : 0x800)); \
        if (all) break;                                                                                      \
        cv = ld_relaxed(inbox);                                                                              \
      }
      while (true) { CAND_STEP(c0) watchdog(n); }
    } else {
      const int t2 = tid - 320;
      if (late && warp == 10) {
        mbar_wait(bar_hx, 0);
        if (elect_one()) {
          tma2d(stage, &maps.wm, (b >> 1) * 32, rank * 512, bar_hw);
          tma2d(stage + 16384, &maps.wm, (b >> 1) * 32, rank * 512 + 256, bar_hw);
        }
      }
      {
        const uint32_t tag = epoch % 3 + 1;
        mbar_wait(bar_hx + 8, 0);
        mbar_wait(bar_hw, 0);
        __nanosleep(late ? OSL2 : OSL);
        {
          const uint32_t t7 = (warp & 1) * 64 + (lane >> 4) * 32 + 16 + (lane & 15);
          const uint32_t* pm = g_modp + ((cj * 128 + t7 * 4) & (DM - 1));
          uint4 m0, m1, m2, m3;
          uint32_t n = 0;
          do {
            m0 = ld_relaxed4(pm); m1 = ld_relaxed4(pm + 2 * DM); m2 = ld_relaxed4(pm + DM); m3 = ld_relaxed4(pm + 3 * DM);
            watchdog(n);
          } while (!__all_sync(0xffffffffu, tag_ok(m0, tag) && tag_ok(m1, tag) && tag_ok(m2, tag) && tag_ok(m3, tag)));
          write_table(par, false, t7, m0, m1);
          write_table(par, true, t7, m2, m3);
          mbar_arrive(bar_mod2);
        }
      }
      mbar_wait(bar_hpub + (warp & 1) * 8, 0);
      PROF(1, t2 == 0, 24);
#pragma unroll 1
      for (int c = 0; c < 8; c++) {
        const uint32_t off = (warp & 1) * UNIT + c * 2048 + lane * 16;
        uint8_t* dst = g_act + (uint32_t)(rb * 80 + cj * 2) * UNIT + off;
        const uint4 v0 = lds4(stage + off), v1 = lds4(stage + off + 512), v2 = lds4(stage + off + 1024), v3 = lds4(stage + off + 1536);
        stg4(dst, v0); stg4(dst + 512, v1); stg4(dst + 1024, v2); stg4(dst + 1536, v3);
      }
      __syncwarp();
      PROF(1, t2 == 0, 15);
      if (lane == 0) {
        mbar_arrive(bar_pread);
        red_release(&g_cnt_h[rb * 32 + cj * 2 + (warp & 1)], 1);
        PROF(1, t2 == 0, 25);
        prefetch_map(&maps.wg); prefetch_map(&maps.wu); prefetch_map(&maps.wd); prefetch_map(&maps.out);
      }
      __syncwarp();
      if (b < NFFN) {
        mbar_wait(bar_go2, 0);
        const __nv_bfloat16* pg = ((b & 1) ? P.w_up : P.w_gate) + (b >> 1) * 64 + (size_t)t2 * FF;
        const __nv_bfloat16* pd = P.w_down + (size_t)b * 32768 + t2 * 64;
        PROF(2, t2 == 0, 13);
#pragma unroll 1
        for (int i = 0; i < WN; i += WB) {
          uint32_t v[WB];
#pragma unroll
          for (int u = 0; u < WB; u++) {
            const int k = i + u;
            asm volatile("ld.global.cg.L2::128B.u32 %0, [%1];" : "=r"(v[u]) : "l"(k < 16 ? pg + (size_t)k * 64 * FF : pd + (k - 16) * 4096));
          }
#pragma unroll
          for (int u = 1; u < WB; u++) v[0] ^= v[u];
          sts1(par + PAR_SINK + t2 * 4, v[0]);
        }
        PROF(2, t2 == 0, 14);
      }
      const uint32_t tag = epoch % 3 + 1;
      mbar_wait(bar_go, 0);
      bar_sync(4, 64);
      if (warp == 10) {
        const uint32_t* src = g_mod + 2 * DM + cj * 128 + lane * 4;
        const uint2 wr = *reinterpret_cast<const uint2*>(P.w_r + cj * 128 + lane * 4);
        uint4 vga, vsb, vcb, vgb;
        uint32_t n = 0;
        do {
          vga = ld_relaxed4(src); vsb = ld_relaxed4(src + DM); vcb = ld_relaxed4(src + 2 * DM); vgb = ld_relaxed4(src + 3 * DM);
          watchdog(n);
        } while (!__all_sync(0xffffffffu, tag_ok(vga, tag) && tag_ok(vsb, tag) && tag_ok(vcb, tag) && tag_ok(vgb, tag)));
        const float c0 = rbf(1.f + bf_hi(vcb.x)), c1 = rbf(1.f + bf_hi(vcb.y)), c2 = rbf(1.f + bf_hi(vcb.z)), c3 = rbf(1.f + bf_hi(vcb.w));
        const float a0 = c0 * bf_lo(wr.x), a1 = c1 * bf_hi(wr.x), a2 = c2 * bf_lo(wr.y), a3 = c3 * bf_hi(wr.y);
        const uint32_t h0 = pack_bf(a0, a1), h1 = pack_bf(a2, a3);
        const uint32_t t1 = par + PAR_T1 + (lane >> 2) * 64 + (lane & 1) * 32 + (lane & 2) * 2;
        sts1(t1, h0); sts1(t1 + 8, pack_bf(a0 - bf_lo(h0), a1 - bf_hi(h0)));
        sts1(t1 + 16, h1); sts1(t1 + 24, pack_bf(a2 - bf_lo(h1), a3 - bf_hi(h1)));
        const uint32_t tg = par + PAR_SINK + (lane >> 3) * 64 + (lane & 1) * 32 + (lane & 6) * 2;
        sts1(tg, __byte_perm(vga.x, vga.y, 0x7632)); sts1(tg + 16, __byte_perm(vga.z, vga.w, 0x7632));
        sts4(par + PAR_T2 + lane * 32, make_uint4(pack_bf(c0, c1), __byte_perm(vsb.x, vsb.y, 0x7632), __byte_perm(vgb.x, vgb.y, 0x7632), __byte_perm(vga.x, vga.y, 0x7632)));
        sts4(par + PAR_T2 + lane * 32 + 16, make_uint4(pack_bf(c2, c3), __byte_perm(vsb.z, vsb.w, 0x7632), __byte_perm(vgb.z, vgb.w, 0x7632), __byte_perm(vga.z, vga.w, 0x7632)));
      } else {
        const uint4 g = poll4((lane & 8) ? g_mod + 8 - (lane & 1) * 4 : g_mod + 5 * DM + (b >> 4) * 128 + (lane & 7) * 16 + (b & 12), tag);
        sts1(par + PAR_CONST + 60, 0);
        if (lane < 8) sts1(par + PAR_CONST + 16 + lane * 4, (b & 2) ? ((b & 1) ? g.w : g.z) : ((b & 1) ? g.y : g.x));
        else if (lane < 10) sts2(par + PAR_CONST + (lane - 8) * 8, __float_as_uint(untag_sum(g.x, g.y) + untag_sum(g.z, g.w)), epoch);
      }
      __syncwarp();
#pragma unroll 4
      for (int q = 0; q < 32; q++) st_b128(g_xch + ((size_t)b * 8 * 256 + q * 64 + t2) * 4, (epoch & 1) << 16, 0, 0, 0);
      for (int q = 0; q < 2; q++) st_relaxed4(g_stats + ((size_t)cj * SEQ + rb * 128 + q * 64 + t2) * 4, 0, 0, 0, 0);
      if (b < NFFN)
        for (int q = 0; q < 2; q++) st_relaxed4(ypart_slot(b, q * 64 + t2), 0, 0, 0, 0);
      st_relaxed4(g_row + rb * 2 * DM + (t2 >> 5) * DM + cj * 128 + (t2 & 31) * 4, 0, 0, 0, 0);
      __threadfence();
      mbar_arrive(bar_par);
      mbar_wait(bar_gate, 0);
      uint32_t have = 0, n = 0;
      while (true) {
        const uint32_t st = lds1(par + PAR_CONST + 60) >> 7;
        if ((st & 31) != have) {
          const uint32_t* hsrc = g_row + (st & 15) * 2 * DM + t2 * 4;
          uint4 hv[4];
          bool ok = true;
#pragma unroll
          for (int i = 0; i < 4; i++) hv[i] = ld_pairs(hsrc + i * 256);
#pragma unroll
          for (int i = 0; i < 4; i++) {
            sts2(base + ((FT_G >> i * 4) & 15) * UNIT + (warp & 1) * 8192 + 256 + lane * 8, hv[i].x, hv[i].z);
            ok = ok && hv[i].y == tag && hv[i].w == tag;
          }
          have = __all_sync(0xffffffffu, ok) ? st & 31 : 0;
        }
        if ((st ^ have) == 32) break;
        watchdog(n);
      }
      mbar_arrive(bar_sel);
    }
    __syncwarp();
    cluster_arrive();
    {
      const uint32_t tag = epoch % 3 + 1, t3 = tid - 256;
      mbar_wait(bar_win, 0);
      uint2 win = lds2(par + PAR_CONST + 56);
      win.y &= 0x7ff;
      const uint32_t* fsrc = g_row + (win.y >> 7) * 2 * DM + (b >> 4) * 128 + (t3 & 7) * 16 + (b & 6) * 2 + ((b >> 2) & 2);
      const uint32_t* ysrc = ypart_slot(min(t3, NFFN - 1), b);
      uint2 fh = ld_pair(fsrc), fx = ld_pair(fsrc + DM);
      uint4 ya = ld_b128(ysrc);
      const float rwin = __uint_as_float(((int)win.x < 0 ? win.x & 0x7fffffffu : ~win.x) & ~0x1ffu);
      const float rs = rbf(rcp(1.f + __expf(-rbf(rwin))));
      uint32_t n = 0;
      while (__any_sync(0xffffffffu, fh.y != tag || fx.y != tag)) { fh = ld_pair(fsrc); fx = ld_pair(fsrc + DM); watchdog(n); }
      while (true) {
        const bool miss = ((ya.x & 1) | (ya.y & 1) << 1) != tag;
        if (!__any_sync(0xffffffffu, miss)) break;
        if (miss) ya = ld_b128(ysrc);
        watchdog(n);
      }
      PROF(8, t3 == 0, 5);
      float y[8] = {bf_lo(ya.x & ~1u), bf_hi(ya.x), bf_lo(ya.y & ~1u), bf_hi(ya.y), bf_lo(ya.z), bf_hi(ya.z), bf_lo(ya.w), bf_hi(ya.w)};
#pragma unroll
      for (int h = 4; h > 0; h >>= 1) {
        const bool up = lane & (h * 2);
#pragma unroll
        for (int e = 0; e < h; e++) y[e] = (up ? y[e + h] : y[e]) + __shfl_xor_sync(0xffffffffu, up ? y[e] : y[e + h], h * 2);
      }
      y[0] += __shfl_xor_sync(0xffffffffu, y[0], 1);
      if (!(lane & 1)) sts1(par + PAR_RED + 64 + t3 * 2, __float_as_uint(y[0]));
      bar_sync(4, 128);
      if (t3 < 8) {
        float y0 = 0.f;
#pragma unroll
        for (int w7 = 0; w7 < 7; w7++) y0 += __uint_as_float(lds1(par + PAR_RED + 64 + w7 * 32 + t3 * 4));
        const uint32_t gv = lds1(par + PAR_CONST + 16 + t3 * 4);
        const uint32_t upd = hmul2(pack_bf(y0, y0), pack_bf(rs, rs));
        const uint32_t r = hadd2(fx.x, hmul2(__byte_perm(gv, gv, 0x3232), hadd2(fh.x, upd)));
        reinterpret_cast<uint16_t*>(P.out)[(size_t)win.y * DM + (b >> 4) * 128 + t3 * 16 + (b & 15)] = (b & 1) ? r >> 16 : r;
        if (b == 0 && t3 == 0) st_relaxed(&g_epoch, epoch + 1);
      }
      PROF(31, t3 == 0, 36);
    }
    cluster_wait();
  } else {
    const int wg = warp >> 2;

    uint32_t tag;
    {
      uint32_t* const pmod = g_modp + rank * 2 * DM + (b >> 1) * 32 + lane;
      uint32_t* const pln = g_ln1 + (rb * 128 + cj * 16 + warp) * 4;
      uint32_t sc[8];
#pragma unroll
      for (int k = 0; k < 8; k++) sc[k] = ldg_nc1(P.c + rank * 512 + warp * 64 + k * 8 + (lane & 3) * 2);
      const uint32_t epoch = ld_relaxed(&g_epoch);
      if (warp == 0) st_relaxed(pmod, 0);
      if (lane == 0) { st_b128(pln, 0, 0, 0, 0); st_b128(pln + 32, 0, 0, 0, 0); }
      asm volatile("setmaxnreg.inc.sync.aligned.u32 232;");
      bar_sync(1, 320);
#pragma unroll
      for (int k = 0; k < 8; k++) sc[k] = pack_bf(silu_f(bf_lo(sc[k])), silu_f(bf_hi(sc[k])));
      keep(sc);
      tag = epoch % 3 + 1;
#pragma unroll
      for (int part = 0; part < 4; part++) {
        if (!(part & 1)) {
          const uint32_t xa = base + (2 + part / 2) * GST_BYTES + warp * 2048 + lane * 16;
          mbar_wait(bar_hx + part * 4, 0);
          float s0 = 0.f, s1 = 0.f, q0 = 0.f, q1 = 0.f;
#pragma unroll
          for (int q = 0; q < 4; q++) {
            const uint4 xv = lds4(xa + q * 512);
            const uint32_t u[4] = {xv.x, xv.y, xv.z, xv.w};
#pragma unroll
            for (int e = 0; e < 4; e++) { const float lo = bf_lo(u[e]), hi = bf_hi(u[e]); s0 += lo; s1 += hi; q0 += lo * lo; q1 += hi * hi; }
          }
          s0 += s1; q0 += q1;
#pragma unroll
          for (int o = 16; o > 0; o >>= 1) { s0 += __shfl_xor_sync(0xffffffffu, s0, o); q0 += __shfl_xor_sync(0xffffffffu, q0, o); }
          const float mean = s0 * (1.f / DM);
          float mb, sd;
          ln_scalars(mean, fmaxf(q0 * (1.f / DM) - mean * mean, 0.f), mb, sd);
          uint32_t ih, il;
          split_inv(sd, ih, il);
          if (lane == 0) st_b128(pln + part * 16, pack_bf(mb, mb), ih, il, tag);
          PROF(1, tid == 0 && part == 2, 4);
        } else if (late == (part == 3)) {
          const uint32_t fr = (lane & 7) + (lane >> 4) * 8, tq = lane & 3;
          const uint32_t wa = stage + warp * 4096 + fr * 64 + ((((lane >> 3) & 1) ^ ((fr >> 1) & 3)) << 4);
          float d0[4] = {0.f, 0.f, 0.f, 0.f}, d1[4] = {0.f, 0.f, 0.f, 0.f};
          mbar_wait(bar_hw, 0);
#pragma unroll
          for (int ks = 0; ks < 4; ks++) {
            uint32_t w[8];
            ldmatrix4t(wa + ks * 1024, w[0], w[1], w[2], w[3]);
            ldmatrix4t((wa ^ 32) + ks * 1024, w[4], w[5], w[6], w[7]);
            mma16816(d0, w[0], w[1], w[2], w[3], sc[2 * ks], sc[2 * ks + 1]);
            mma16816(d1, w[4], w[5], w[6], w[7], sc[2 * ks], sc[2 * ks + 1]);
          }
          sts1(base + 2 * GST_BYTES + warp * 2048 + (tq * 8 + (lane >> 2)) * 4, __float_as_uint((tq & 2) ? ((tq & 1) ? d1[2] : d1[0]) : ((tq & 1) ? d0[2] : d0[0])));
          bar_sync(1, 256);
          if (warp == 0) {
            float s = 0.f;
#pragma unroll
            for (int w8 = 0; w8 < 8; w8++) s += __uint_as_float(lds1(base + 2 * GST_BYTES + w8 * 2048 + lane * 4));
            st_relaxed(pmod, (__float_as_uint(s) & ~3u) | tag);
          }
          PROF(1, tid == 0, 3);
        }
      }
      cluster_wait();
      if (wg == 1) bar_arrive(2, 256);
    }

    float f0 = 0.f, f1 = 0.f;
    const uint32_t rempty = lane < 2 ? mapa(bempty, lane & 1) : 0;
    constexpr uint32_t GE = NSLOT * 8 + 32;
    float o[64], s[64];
#pragma unroll 1
    for (int ps = 0; ps < 3; ps++) {
      {
        const uint32_t xt = ps == 1 ? XT1 : XT2, wt = ps == 1 ? WT1 : WT2;
        const int nst = ps == 2 ? 28 : 14;
        if (ps == 0) {
          float ga[64], gb[64];
#pragma unroll
          for (int i = 0; i < 64; i++) { ga[i] = 0.f; gb[i] = 0.f; }
          uint32_t a[2][16];
          const uint32_t l = fresh_lane();
          uint32_t fa[4];
#pragma unroll
          for (int kk = 0; kk < 4; kk++) fa[kk] = (base + wg * 8192 + frag_offset(warp)) ^ (kk * 32);
          const uint32_t mt = par + (l & 3) * 16;
          auto fetch = [&](int i, uint32_t (&f)[16], uint32_t z) {
            mbar_wait(xfull + (i & 3) * 8, i >> 2);
#pragma unroll
            for (int kk = 0; kk < 4; kk++) ldmatrix4(fa[kk] + (i & 3) * GST_BYTES + z, f[4 * kk], f[4 * kk + 1], f[4 * kk + 2], f[4 * kk + 3]);
          };
          const bool oddw = warp & 2;
          uint4 r0, r1;
          {
            const uint32_t t7 = (warp & 1) * 64 + (l >> 4) * 32 + (l & 15);
            const uint32_t* pm = g_modp + wg * DM + ((cj * 128 + t7 * 4) & (DM - 1));
            const uint32_t* pr = g_ln1 + (rb * 128 + warp * 16 + (l >> 2)) * 4;
            uint4 m0 = make_uint4(tag, tag, tag, tag), m1 = m0;
            if (!oddw) { m0 = ld_relaxed4(pm); m1 = ld_relaxed4(pm + 2 * DM); }
            r0 = ld_b128(pr); r1 = ld_b128(pr + 32);
            fetch(0, a[0], 0); fetch(1, a[1], 0);
            uint32_t n = 0;
            bool written = false;
#pragma unroll 1
            while (true) {
              uint32_t miss;
              asm volatile("{ .reg .pred p0, p1, p2, p3; .reg .b32 t, u;\n"
                           "lop3.b32 t, %1, %2, %19, 0x7e; lop3.b32 u, %3, %4, %19, 0x7e; or.b32 t, t, u; and.b32 t, t, 3; setp.ne.u32 p0, t, 0;\n"
                           "lop3.b32 t, %5, %6, %19, 0x7e; lop3.b32 u, %7, %8, %19, 0x7e; or.b32 t, t, u; and.b32 t, t, 3; setp.ne.u32 p1, t, 0;\n"
                           "setp.ne.u32 p2, %12, %19; setp.ne.u32 p3, %16, %19;\n"
                           "@p0 ld.relaxed.gpu.global.v4.u32 {%1, %2, %3, %4}, [%17];\n"
                           "@p1 ld.relaxed.gpu.global.v4.u32 {%5, %6, %7, %8}, [%17 + 8192];\n"
                           "@p2 ld.relaxed.gpu.global.v4.u32 {%9, %10, %11, %12}, [%18];\n"
                           "@p3 ld.relaxed.gpu.global.v4.u32 {%13, %14, %15, %16}, [%18 + 128];\n"
                           "or.pred p0, p0, p1; or.pred p2, p2, p3; vote.sync.any.pred p0, p0, 0xffffffff; vote.sync.any.pred p2, p2, 0xffffffff;\n"
                           "selp.u32 t, 1, 0, p0; selp.u32 u, 2, 0, p2; or.b32 %0, t, u; }"
                           : "=r"(miss), "+r"(m0.x), "+r"(m0.y), "+r"(m0.z), "+r"(m0.w), "+r"(m1.x), "+r"(m1.y), "+r"(m1.z), "+r"(m1.w),
                             "+r"(r0.x), "+r"(r0.y), "+r"(r0.z), "+r"(r0.w), "+r"(r1.x), "+r"(r1.y), "+r"(r1.z), "+r"(r1.w)
                           : "l"(pm), "l"(pr), "r"(tag) : "memory");
              if (!(miss & 1) && !written) {
                written = true;
                if (!oddw) write_table(par, wg, t7, m0, m1);
                mbar_arrive(bar_mod);
              }
              if (!miss) break;
              watchdog(n);
            }
          }
          const uint32_t zero = r0.w ^ tag;
          auto normalize = [&](uint32_t (&f)[16]) {
#pragma unroll
            for (int k = 0; k < 16; k += 2) { f[k] = ln_norm(f[k], r0.x, r0.y, r0.z); f[k + 1] = ln_norm(f[k + 1], r1.x, r1.y, r1.z); }
          };
          auto modulate = [&](int i, uint32_t (&f)[16]) {
#pragma unroll
            for (int kk = 0; kk < 4; kk++) {
              const uint4 m = lds4(mt + slice_of(i) * 256 + kk * 64);
              f[4 * kk] = hfma2(f[4 * kk], m.x, m.z); f[4 * kk + 1] = hfma2(f[4 * kk + 1], m.x, m.z);
              f[4 * kk + 2] = hfma2(f[4 * kk + 2], m.y, m.w); f[4 * kk + 3] = hfma2(f[4 * kk + 3], m.y, m.w);
            }
            keep(f);
            mbar_arrive_pred(xempty + (i & 3) * 8, l == 0);
          };
          auto publish = [&](int u, uint32_t (&f)[16]) {
#pragma unroll
            for (int kk = 0; kk < 4; kk++) stmatrix4(fa[kk] + OFF_STAGE + u * UNIT, f[4 * kk], f[4 * kk + 1], f[4 * kk + 2], f[4 * kk + 3]);
            __syncwarp();
            mbar_arrive_pred(bar_hpub + u * 8, l == 0);
          };
          auto multiply = [&](int i, uint32_t (&f)[16]) {
            mbar_wait(gfull + (i & 3) * 8, i >> 2);
            const uint64_t db = make_desc(base + (i & 3) * GST_BYTES + UNIT, 8192, 1024);
            wg_fence();
#pragma unroll
            for (int kk = 0; kk < 4; kk++) mma256_rs(ga, gb, f[4 * kk], f[4 * kk + 1], f[4 * kk + 2], f[4 * kk + 3], db + kk * 128);
            wg_commit();
          };
          auto next = [&](int i, uint32_t (&f)[16]) {
            wg_wait<1>();
            mbar_arrive_cl(rempty, GE + ((i + 2) & 3) * 8);
            uint32_t z = zero;
#pragma unroll
            for (int k = 0; k < 16; k += 2) asm volatile("lop3.b32 %0, %1, %2, %0, 0xA8;" : "+r"(z) : "r"(f[k]), "r"(f[k + 1]));
            fetch(i, f, z);
            normalize(f);
            if (i == 2) { keep(f); mbar_wait(bar_mod2, 0); }
            modulate(i, f); multiply(i, f);
          };
          normalize(a[0]); normalize(a[1]);
          keep(a[0]); keep(a[1]);
          mbar_wait(bar_mod, 0);
          PROF(1, tid == 0, 2);
          modulate(0, a[0]); multiply(0, a[0]); publish(0, a[0]);
          modulate(1, a[1]); multiply(1, a[1]);
#pragma unroll 1
          for (int i = 2; i < NRS; i += 2) {
            next(i, a[0]);
            if (i == 2) publish(1, a[0]);
            next(i + 1, a[1]);
          }
          wg_wait<1>();
          mbar_arrive_cl(rempty, GE + ((NRS + 2) & 3) * 8);
#pragma unroll 1
          for (int i = NRS; i < 14; i++) {
            mbar_wait(xfull + (i & 3) * 8, (i >> 2) & 1);
            mbar_wait(gfull + (i & 3) * 8, (i >> 2) & 1);
            const uint32_t xa = base + (i & 3) * GST_BYTES;
            const uint64_t da = make_desc(xa + wg * 8192, 16, 1024), db = make_desc(xa + UNIT, 8192, 1024);
            if (i == 13) bar_sync(2 + wg, 256);
            wg_fence();
#pragma unroll
            for (int kk = 0; kk < 4; kk++) mma256_ss(ga, gb, da + kk * 2, db + kk * 128, 1);
            wg_commit();
            if (i == 13) bar_arrive(3 - wg, 256);
            wg_wait<1>();
            uint32_t z = zero;
#pragma unroll
            for (int k = 0; k < 16; k += 2) asm volatile("lop3.b32 %0, %1, %2, %0, 0xA8;" : "+r"(z) : "r"(a[1][k]), "r"(a[1][k + 1]));
            mbar_arrive_cl(rempty, GE + ((i + 3) & 3) * 8 + z);
            mbar_arrive_pred(xempty + ((i + 3) & 3) * 8, l == 0 && i != NRS);
          }
          mbar_wait(xfull + 16, 1);
          wg_wait<0>();
          keep(ga); keep(gb);
#pragma unroll
          for (int i = 0; i < 64; i++) {
            asm volatile("mov.b32 %0, %1;" : "=f"(s[i]) : "f"(ga[i]));
            asm volatile("mov.b32 %0, %1;" : "=f"(o[i]) : "f"(gb[i]));
          }
        } else {
          float ga[64], gb[64];
#pragma unroll
          for (int i = 0; i < 64; i++) {
            asm volatile("mov.b32 %0, %1;" : "=f"(ga[i]) : "f"(s[i]));
            asm volatile("mov.b32 %0, %1;" : "=f"(gb[i]) : "f"(o[i]));
          }
#pragma unroll 1
          for (int i = 0; i < nst; i++) {
            mbar_wait(gfull + (i & 3) * 8, (i >> 2) & 1);
            const uint64_t da = make_desc(base + unit_of(xt, i & 3) + wg * 8192, 16, 1024), db = make_desc(base + unit_of(wt, i & 3), 8192, 1024);
            if (i == nst - 1) bar_sync(2 + wg, 256);
            wg_fence();
#pragma unroll
            for (int kk = 0; kk < 4; kk++) mma256_ss(ga, gb, da + kk * 2, db + kk * 128, kk ? 1 : i);
            wg_commit();
            if (i == nst - 1) bar_arrive(3 - wg, 256);
            wg_wait<1>();
            mbar_arrive_cl(rempty, GE + ((i + 3) & 3) * 8, i != 0);
            PROF(4, tid == 0 && (i & 3) == 0, 40 + (ps - 1) * 4 + i / 4);
          }
          wg_wait<0>();
          keep(ga); keep(gb);
#pragma unroll
          for (int i = 0; i < 64; i++) {
            asm volatile("mov.b32 %0, %1;" : "=f"(s[i]) : "f"(ga[i]));
            asm volatile("mov.b32 %0, %1;" : "=f"(o[i]) : "f"(gb[i]));
          }
        }
        mbar_arrive_cl(rempty, GE + (ps == 2 ? 24 : 8));
        if (ps == 2) break;
      }
      const uint32_t qw = base + wg * 8192, qt = QT >> (16 * ps), at = ps ? AT1 : AT0;
      {
        const uint32_t wt = ps ? WT1 : WT0;
        const uint64_t da0 = make_desc(qw + unit_of(qt, 2), 16, 1024), da1 = make_desc(qw + unit_of(qt, 3), 16, 1024);
        const uint64_t db0 = make_desc(base + unit_of(wt, 2), 8192, 1024), db1 = make_desc(base + unit_of(wt, 3), 8192, 1024);
        mbar_wait(gfull + 16, 1);
        bar_sync(2 + wg, 256);
        wg_fence();
#pragma unroll
        for (int kk = 0; kk < 4; kk++) mma_ss<1>(s, da0 + kk * 2, db0 + kk * 128, 1);
        wg_commit();
        mbar_wait(xfull + 24, 1);
        mbar_wait(gfull + 24, 1);
        wg_fence();
#pragma unroll
        for (int kk = 0; kk < 4; kk++) mma_ss<1>(s, da1 + kk * 2, db1 + kk * 128, 1);
        wg_commit();
        bar_arrive(3 - wg, 256);
        mbar_wait(ps == 0 ? bar_pread : bar_ofree + 8, 0);
        wg_wait<0>();
        keep(s);
        PROF(2, tid == 0, 8 + ps * 8);
        uint32_t q[32];
        pack_p(s, q);
#pragma unroll
        for (int i = 0; i < 4; i++) stmatrix4((qw + unit_of(qt, 0) + frag_offset(warp)) ^ (i << 5), q[4 * i], q[4 * i + 1], q[4 * i + 2], q[4 * i + 3]);
        keep(q);
        bar_sync(2 + wg, 256);
        wg_fence();
#pragma unroll
        for (int kk = 0; kk < 8; kk++) mma_ss<1>(o, (kk < 4 ? da0 : da1) + (kk & 3) * 2, (kk < 4 ? db0 : db1) + UNIT / 16 + (kk & 3) * 128, 1);
        wg_commit();
        mbar_wait(bfull, 0);
        wg_fence();
        const uint64_t dk = make_desc(base + unit_of(at, 0), 16, 1024);
#pragma unroll
        for (int kk = 0; kk < 8; kk++) mma_rs<0>(s, q[4 * kk], q[4 * kk + 1], q[4 * kk + 2], q[4 * kk + 3], dk + (kk >> 2) * 1024 + (kk & 3) * 2, kk != 0);
        wg_commit();
        bar_arrive(3 - wg, 256);
#pragma unroll
        for (int i = 4; i < 8; i++) stmatrix4((qw + unit_of(qt, 1) + frag_offset(warp)) ^ ((i & 3) << 5), q[4 * i], q[4 * i + 1], q[4 * i + 2], q[4 * i + 3]);
        wg_wait<1>();
        keep(o);
        mbar_arrive_cl(rempty, GE + 16);
        mbar_arrive_cl(rempty, GE + 24);
        store_chunk<0>(o, qw + unit_of(qt, 2) + frag_offset(warp));
        store_chunk<1>(o, qw + unit_of(qt, 3) + frag_offset(warp));
        wg_wait<0>();
        keep(s);
        mbar_arrive_cl(rempty, 0);
      }
      PROF(4, tid == 0 && ps == 1, 61);
      float l0 = 0.f, l1 = 0.f;
      auto step = [&](auto odd_c, const int j, uint32_t (&pw)[32], uint32_t (&pr)[32]) {
        constexpr bool ODD = decltype(odd_c)::value;
        const bool first = !ODD && (j & 2) == 0, last = ODD && j == 7;
        const uint32_t ph = (j >> 1) & 1;
        float i0, i1, a0, a1;
        const bool so = !ODD && j == 4;
        if (so) { i0 = inv_quad_sum(l0); i1 = inv_quad_sum(l1); l0 = 0.f; l1 = 0.f; }
        bool redo = !ODD && (j | ps) == 0;
        while (true) {
          if (redo) {
            float m0 = fmaxf(s[0], s[1]), m1 = fmaxf(s[2], s[3]);
#pragma unroll
            for (int i = 1; i < 16; i++) { m0 = fmaxf(m0, fmaxf(s[4 * i], s[4 * i + 1])); m1 = fmaxf(m1, fmaxf(s[4 * i + 2], s[4 * i + 3])); }
            m0 = fmaxf(m0, __shfl_xor_sync(0xffffffffu, m0, 1)); m1 = fmaxf(m1, __shfl_xor_sync(0xffffffffu, m1, 1));
            m0 = fmaxf(m0, __shfl_xor_sync(0xffffffffu, m0, 2)); m1 = fmaxf(m1, __shfl_xor_sync(0xffffffffu, m1, 2));
            m0 *= SCL2; m1 *= SCL2;
            if (!first) {
              m0 = fmaxf(m0, f0); m1 = fmaxf(m1, f1);
              const float c0 = ex2(f0 - m0), c1 = ex2(f1 - m1);
              l0 *= c0; l1 *= c1;
              wg_wait<0>();
              keep(o);
#pragma unroll
              for (int i = 0; i < 16; i++) { o[4 * i] *= c0; o[4 * i + 1] *= c0; o[4 * i + 2] *= c1; o[4 * i + 3] *= c1; }
            }
            f0 = m0; f1 = m1;
          }
          float b0 = 0.f, b1 = 0.f;
          a0 = 0.f; a1 = 0.f;
#pragma unroll
          for (int i = 0; i < 16; i++) {
            const float e0 = ex2(fmaf(s[4 * i], SCL2, -f0)), e1 = ex2(fmaf(s[4 * i + 1], SCL2, -f0));
            const float e2 = ex2(fmaf(s[4 * i + 2], SCL2, -f1)), e3 = ex2(fmaf(s[4 * i + 3], SCL2, -f1));
            a0 += e0; b0 += e1; a1 += e2; b1 += e3;
            pw[2 * i] = pack_bf(e0, e1); pw[2 * i + 1] = pack_bf(e2, e3);
            if (i == VREL) {
#pragma unroll
              for (int k = 0; k < 2 * VREL + 2; k++) asm volatile("" : "+r"(pw[k])::"memory");
              mbar_wait(bar_mod, 0);
              wg_wait<0>();
              mbar_arrive_cl(rempty, ODD ? 16 : 0, !redo && (ODD || j));
#pragma unroll
              for (int k = 4 * VREL + 4; k < 64; k++) asm volatile("" : "+f"(s[k])::"memory");
            }
          }
          a0 += b0; a1 += b1;
          if (redo) break;
          redo = __any_sync(0xffffffffu, !(a0 + a1 < 0x1p90f));
          if (first) {
            uint32_t m0 = __ballot_sync(0xffffffffu, a0 > 0x1p-80f), m1 = __ballot_sync(0xffffffffu, a1 > 0x1p-80f);
            m0 |= m0 >> 1; m1 |= m1 >> 1; m0 |= m0 >> 2; m1 |= m1 >> 2;
            redo = redo || (m0 & m1 & 0x11111111u) != 0x11111111u;
          }
          if (!redo) break;
        }
        l0 += a0; l1 += a1;
        keep(pw);
        keep(o);
        if (so) store_chunk<0>(o, i0, i1, qw + unit_of(qt, 0) + frag_offset(warp));
        keep(o);
        if (j == (ODD ? 5 : 0)) { fence_async_smem(); if (ODD) mbar_arrive(bar_ofull + wg * 8); }
        mbar_wait(bfull + (ODD ? 24 : 8), ph);
        bar_sync(2 + wg, 256);
        if (!last) {
          const uint32_t qn = qt >> (j >= 3 ? 8 : 0);
          wg_fence();
          issue_qk(s, qw + unit_of(qn, 0), qw + unit_of(qn, 1), base + unit_of(at, ODD ? 3 : 1));
          wg_commit();
          mbar_wait(bfull + (ODD ? 0 : 16), ODD ? ph ^ 1 : ph);
        }
        if (so) { store_chunk<1>(o, i0, i1, qw + unit_of(qt, 1) + frag_offset(warp)); keep(o); }
        wg_fence();
        issue_pv(o, pw, base + unit_of(at, ODD ? (last ? 3 : 0) : 2), !first);
        wg_commit();
        bar_arrive(3 - wg, 256);
        wg_wait<1>();
        keep(s);
        mbar_arrive_cl(rempty, ODD ? 24 : 8, !last);
        PROF(4, tid == 0 && ps == 1, 51 + j);
      };
      uint32_t pa[32], pb[32];
#pragma unroll 1
      for (int j = 0; j < 8; j += 2) {
        step(std::false_type{}, j, pa, pb);
        step(std::true_type{}, j + 1, pb, pa);
      }
      {
        const float i0 = inv_quad_sum(l0), i1 = inv_quad_sum(l1);
        wg_wait<0>();
        keep(o);
        mbar_arrive_cl(rempty, 24);
        store_chunk<0>(o, i0, i1, qw + unit_of(qt, 2) + frag_offset(warp));
        store_chunk<1>(o, i0, i1, qw + unit_of(qt, 3) + frag_offset(warp));
        fence_async_smem();
        mbar_arrive(bar_ofull + 16 + wg * 8);
      }
      PROF(2, tid == 0, 10 + ps * 8);
    }

    const int ln = fresh_lane(), g = ln >> 2, tq = ln & 3, ct = warp * 32 + ln;
    const bool lane0 = ln == 0;
    const int lrow0 = warp * 16 + g;
    const int grow0 = rb * 128 + lrow0;
    const uint32_t res = base + OFF_RES, trow = res + wg * 8192 + frag_offset(warp);
    uint32_t xr[32];
    uint4 sv[4], own;
    uint32_t* sp[4];
#pragma unroll
    for (int k = 0; k < 4; k++) sp[k] = g_stats + ((((tq >> 1) * 4 + k) ^ cj) * SEQ + grow0 + (tq & 1) * 8) * 4;
    {
      const uint64_t da = make_desc(base + wg * 8192, 16, 1024), db = make_desc(base, 8192, 1024);
      constexpr int U = UNIT / 16;
#define HALF_STAGE(acc, xu, wu) _Pragma("unroll") for (int kk = 0; kk < 4; kk++) mma_ss<1>(acc, da + (xu) * U + kk * 2, db + (wu) * U + kk * 128, 1)
      PROF(10, ct == PT, 19); STAMP(0);
      cluster_arrive();
      mbar_wait(gfull, 1);
      mbar_wait(gfull + 8, 1);
      bar_sync(2 + wg, 256);
      wg_fence();
      HALF_STAGE(o, 7, 1);
      HALF_STAGE(o, 8, 3);
      wg_commit();
      STAMP(16);
      mbar_wait(gfull + 16, 1);
      STAMP(17);
      wg_fence();
      HALF_STAGE(o, 6, 11);
      wg_commit();
      bar_arrive(3 - wg, 256);
      mbar_wait(bar_par, 0);
      uint32_t* xo = g_xch + ((size_t)b * 8 * 256 + ct) * 4;
      const uint32_t* xi = g_xch + ((size_t)(b ^ 2) * 8 * 256 + ct) * 4;
      const uint32_t par1 = (~lds1(par + PAR_CONST + 4) & 1) << 16;
      wg_wait<1>();
      mbar_arrive_pred(bar_rel, lane0);
      wg_wait<0>();
      keep(o);
      mbar_arrive_pred(bar_ring, lane0);
      PROF(8, ct == PT, 20); STAMP(1);
#define SEND(i) st_b128(xo + (i) * 1024, (pack_bf(o[8 * (i)], o[8 * (i) + 1]) & ~0x10000u) | par1, pack_bf(o[8 * (i) + 2], o[8 * (i) + 3]), \
                        pack_bf(o[8 * (i) + 4], o[8 * (i) + 5]), pack_bf(o[8 * (i) + 6], o[8 * (i) + 7]))
#pragma unroll
      for (int i = 0; i < NS1; i++) SEND(i);
      PROF(8, ct == PT, 21); STAMP(2);
      bar_sync(2 + wg, 256);
      wg_fence();
      HALF_STAGE(s, 7, 0);
      HALF_STAGE(s, 8, 2);
      HALF_STAGE(s, 6, 10);
      wg_commit();
      bar_arrive(3 - wg, 256);
      STAMP(18);
      mbar_wait(gfull + 24, 1);
#pragma unroll
      for (int i = NS1; i < 8; i++) SEND(i);
      uint4 v[8];
      STAMP(19);
      mbar_wait(bar_xres, 0);
      wg_wait<0>();
      mbar_arrive_pred(bar_ring + 8, lane0);
      bar_sync(2 + wg, 256);
      STAMP(20);
#pragma unroll
      for (int i = 0; i < LD2; i++) v[i] = ld_b128(xi + i * 1024);
      mbar_wait(bar_xres, 0);
      wg_fence();
      HALF_STAGE(s, 9, 4);
      wg_commit();
      mbar_wait(bar_rx, 0);
      wg_fence();
      HALF_STAGE(s, 1, 5);
      wg_commit();
      bar_arrive(3 - wg, 256);
      STAMP(21);
#pragma unroll
      for (int i = LD2; i < 8; i++) v[i] = ld_b128(xi + i * 1024);
      mbar_wait(bar_xres, 0);
      wg_wait<0>();
      keep(s);
      mbar_arrive_pred(bar_ring + 16, lane0);
      PROF(10, ct == PT, 23); STAMP(4);
#pragma unroll
      for (int i = 0; i < 16; i += 2) ldmatrix4((trow ^ ((i & 7) << 4)) + (i >> 3) * 16384, xr[2 * i], xr[2 * i + 1], xr[2 * i + 2], xr[2 * i + 3]);
      uint32_t ga[16];
      uint4 bw[8];
#pragma unroll
      for (int i = 0; i < 8; i++) {
        if (!(i & 1)) {
          const uint4 t = lds4(par + PAR_SINK + i * 32 + tq * 16);
          ga[2 * i] = t.x; ga[2 * i + 1] = t.y; ga[2 * i + 2] = t.z; ga[2 * i + 3] = t.w;
        }
        bw[i] = lds4(par + PAR_T1 + i * 64 + tq * 16);
        if (!(g & 1)) { bw[i].x = 0x3f803f80u; bw[i].y = 0x3f803f80u; }
      }
      uint32_t pk[32];
      pack_p(s, pk);
      keep(pk);
      {
        uint32_t n = 0, miss;
        do {
          miss = 0;
#pragma unroll
          for (int i = 0; i < 8; i++) miss |= v[i].x ^ par1;
          miss = __any_sync(0xffffffffu, miss & 0x10000u);
          if (miss) {
#pragma unroll
            for (int i = 0; i < 8; i++)
              asm volatile("{ .reg .pred p; .reg .b32 t; xor.b32 t, %0, %5; and.b32 t, t, 0x10000; setp.ne.u32 p, t, 0;\n"
                           "@p ld.relaxed.gpu.global.v4.u32 {%0, %1, %2, %3}, [%4]; }"
                           : "+r"(v[i].x), "+r"(v[i].y), "+r"(v[i].z), "+r"(v[i].w) : "l"(xi + i * 1024), "r"(par1) : "memory");
          }
          watchdog(n);
        } while (miss);
      }
      PROF(8, ct == PT, 22); STAMP(3);
      float ds[4] = {0.f, 0.f, 0.f, 0.f}, dl[4] = {0.f, 0.f, 0.f, 0.f}, q0[4] = {0.f, 0.f, 0.f, 0.f}, q1[4] = {0.f, 0.f, 0.f, 0.f};
#pragma unroll
      for (int i = 0; i < 8; i++) {
        const uint32_t u0 = hfma2(ga[2 * i], hadd2(pk[4 * i], v[i].x & ~0x10000u), xr[4 * i]);
        const uint32_t u1 = hfma2(ga[2 * i], hadd2(pk[4 * i + 1], v[i].y), xr[4 * i + 1]);
        const uint32_t u2 = hfma2(ga[2 * i + 1], hadd2(pk[4 * i + 2], v[i].z), xr[4 * i + 2]);
        const uint32_t u3 = hfma2(ga[2 * i + 1], hadd2(pk[4 * i + 3], v[i].w), xr[4 * i + 3]);
        xr[4 * i] = u0; xr[4 * i + 1] = u1; xr[4 * i + 2] = u2; xr[4 * i + 3] = u3;
        mma16816(ds, u0, u1, u2, u3, bw[i].x, bw[i].y);
        mma16816(dl, u0, u1, u2, u3, bw[i].z, bw[i].w);
        mma16816(q0, u0, u1, u2, u3, u0, u2);
        mma16816(q1, u0, u1, u2, u3, u1, u3);
      }
      const float sqa = __shfl_sync(0xffffffffu, (g & 1) ? q0[1] : q0[0], g * 4 + (g >> 1));
      const float sqb = __shfl_sync(0xffffffffu, (g & 1) ? q1[3] : q1[2], g * 4 + (g >> 1));
      own = (tq & 1) ? make_uint4(__float_as_uint(ds[2]), __float_as_uint(sqb), __float_as_uint(ds[3] + dl[3]), tag)
                                 : make_uint4(__float_as_uint(ds[0]), __float_as_uint(sqa), __float_as_uint(ds[1] + dl[1]), tag);
      if (tq < 2) st_b128(sp[0], own.x, own.y, own.z, own.w);
#pragma unroll
      for (int k = 0; k < 4; k++) sv[k] = make_uint4(0, 0, 0, 0);
    }
    PROF(8, ct == PT, 29); STAMP(5);
    uint32_t mm, ih, il;
    float rbest;
    uint32_t wf[128];
    const uint32_t frow = (ln & 7) + (ln >> 4) * 8;
    const uint32_t wfo = base + (warp & 1) * 8192 + frow * 64 + ((((ln >> 3) & 1) ^ ((frow >> 1) & 3)) << 4);
#define LOAD_WF(m) _Pragma("unroll") for (int f = 0; f < 16; f++) {                                                   \
      const int r = ((f >> 1) * 4 + (m) * 2 + (f & 1)) * 4;                                                           \
      ldmatrix4t(((wfo + unit_of((m) ? FT_U : FT_G, warp >> 1)) ^ ((f & 1) * 32)) + (f >> 1) * 1024, wf[r], wf[r + 1], wf[r + 2], wf[r + 3]); \
    }
    bool early;
    {
#pragma unroll
      for (int i = 0; i < 16; i += 2) stmatrix4((trow ^ ((i & 7) << 4)) + (i >> 3) * 16384, xr[2 * i], xr[2 * i + 1], xr[2 * i + 2], xr[2 * i + 3]);
      const uint4 cst = lds4(par + PAR_CONST);
      const float A1 = __uint_as_float(cst.x), A2 = __uint_as_float(cst.z);
      uint32_t n = 0;
      early = false;
#pragma unroll 1
      while (true) {
        uint32_t miss;
        asm volatile("{ .reg .pred p0, p1, p2, p3; .reg .b64 u, v; .reg .b128 w;\n"
                     "setp.ge.u32 p0, %22, 2; setp.ne.and.u32 p0, %4, %21, p0; setp.ne.u32 p1, %8, %21; setp.ne.u32 p2, %12, %21; setp.ne.u32 p3, %16, %21;\n"
                     "@p0 ld.relaxed.gpu.global.v4.u32 {%1, %2, %3, %4}, [%17];\n"
                     "@p1 ld.relaxed.gpu.global.v4.u32 {%5, %6, %7, %8}, [%18];\n"
                     "@p2 ld.relaxed.gpu.global.v4.u32 {%9, %10, %11, %12}, [%19];\n"
                     "@p3 ld.relaxed.gpu.global.v4.u32 {%13, %14, %15, %16}, [%20];\n"
                     "or.pred p0, p0, p1; or.pred p2, p2, p3; or.pred p0, p0, p2; vote.sync.any.pred p0, p0, 0xffffffff; selp.u32 %0, 1, 0, p0; }"
                     : "=r"(miss), "+r"(sv[0].x), "+r"(sv[0].y), "+r"(sv[0].z), "+r"(sv[0].w), "+r"(sv[1].x), "+r"(sv[1].y), "+r"(sv[1].z), "+r"(sv[1].w),
                       "+r"(sv[2].x), "+r"(sv[2].y), "+r"(sv[2].z), "+r"(sv[2].w), "+r"(sv[3].x), "+r"(sv[3].y), "+r"(sv[3].z), "+r"(sv[3].w)
                     : "l"(sp[0]), "l"(sp[1]), "l"(sp[2]), "l"(sp[3]), "r"(tag), "r"(tq) : "memory");
        if (!miss) break;
        if (!early && (b >= NFFN || __all_sync(0xffffffffu, mbar_test(bar_box + (warp >> 1) * 8, 0)))) {
          early = true;
          LOAD_WF(0);
          __syncwarp();
          mbar_arrive_pred(bar_gate, lane0);
        }
        watchdog(n);
      }
      const uint4 v0 = tq < 2 ? own : sv[0], v1 = sv[1], v2 = sv[2], v3 = sv[3];
      PROF(8, ct == PT, 30); STAMP(6);
      float su = (__uint_as_float(v0.x) + __uint_as_float(v1.x)) + (__uint_as_float(v2.x) + __uint_as_float(v3.x));
      float sq = (__uint_as_float(v0.y) + __uint_as_float(v1.y)) + (__uint_as_float(v2.y) + __uint_as_float(v3.y));
      float dt = (__uint_as_float(v0.z) + __uint_as_float(v1.z)) + (__uint_as_float(v2.z) + __uint_as_float(v3.z));
      su += __shfl_xor_sync(0xffffffffu, su, 2); sq += __shfl_xor_sync(0xffffffffu, sq, 2); dt += __shfl_xor_sync(0xffffffffu, dt, 2);
      const float m = su * (1.f / DM);
      float mb, sd;
      ln_scalars(m, fmaxf(sq * (1.f / DM) - m * m, 0.f), mb, sd);
      const float inv = rcp(sd);
      rbest = (dt - mb * A1) * inv + A2;
      mm = pack_bf(mb, mb);
      ih = pack_bf(inv, inv);
      const float lo = inv - bf_lo(ih);
      il = pack_bf(lo, lo);
    }
    int ibest;
    {
      const uint32_t bits = __float_as_uint(rbest);
      const uint32_t key = (((int)bits < 0 ? ~bits : bits | 0x80000000u) & ~0x1ffu) | ((127 - lrow0 - (tq & 1) * 8) << 2) | tag;
      sts1(par + PAR_RED + warp * 4, __reduce_max_sync(0xffffffffu, key));
      PROF(8, ct == PT, 38); STAMP(7);
      bar_sync(1, 256);
      const uint4 ka = lds4(par + PAR_RED), kb = lds4(par + PAR_RED + 16);
      const uint32_t k2 = max(max(max(ka.x, ka.y), max(ka.z, ka.w)), max(max(kb.x, kb.y), max(kb.z, kb.w)));
      if (ct < CR && cj == 0) st_relaxed(g_cand + ct * 512 + rb * CS, k2);
      ibest = 127 - ((k2 >> 2) & 127);
    }
    PROF(8, ct == PT, 39); STAMP(8);
    if ((ibest >> 4) == warp) {
      const int src = (ibest & 7) * 4 + ((ibest >> 3) & 1), ch = g * 2;
      const uint32_t cm = __shfl_sync(0xffffffffu, mm, src), ch_ = __shfl_sync(0xffffffffu, ih, src), cl = __shfl_sync(0xffffffffu, il, src);
      const uint32_t xa = res + (ch >> 3) * 16384 + ibest * 128 + (((ch & 7) ^ (ibest & 7)) << 4) + tq * 4;
      const uint32_t x0 = lds1(xa), x1 = lds1(xa ^ 16);
      const uint2 p0 = lds2(par + PAR_T2 + ch * 64 + tq * 16), p1 = lds2(par + PAR_T2 + ch * 64 + 64 + tq * 16);
      uint32_t* dst = g_row + rb * 2 * DM + cj * 128 + ln * 4;
      st_pairs(dst, ln_mod(x0, cm, ch_, cl, p0.x, p0.y), ln_mod(x1, cm, ch_, cl, p1.x, p1.y), tag);
      st_pairs(dst + DM, x0, x1, tag);
      __syncwarp();
    }
    PROF(8, ct == PT, 37); STAMP(9);
    uint32_t wd[64];
    const uint32_t wda = base + unit_of(FT_D, warp >> 1) + (warp & 1) * 8192 + frow * 128 + ((((ln >> 3) & 1) ^ (ln & 7)) << 4);
#define LOAD_WD(f) ldmatrix4t((wda ^ ((((f) >> 1) & 3) * 32)) + ((f) >> 3) * 4096 + ((f) & 1) * 2048, wd[4 * (f)], wd[4 * (f) + 1], wd[4 * (f) + 2], wd[4 * (f) + 3])
    if (!early) {
      if (b < NFFN) mbar_wait(bar_box + (warp >> 1) * 8, 0);
      LOAD_WF(0);
      __syncwarp();
      mbar_arrive_pred(bar_gate, lane0);
    }
    if (b < NFFN) {
      const uint32_t own = base + unit_of(FT_G, warp >> 1) + (warp & 1) * 8192;
      mbar_wait(bar_box + (4 + (warp >> 1)) * 8, 0);
      LOAD_WF(1);
      uint32_t* const ydst = ypart_slot(b, warp * 16 + (tq & 1) * 8 + g);
      PROF(8, ct == PT, 31); STAMP(10);
      bool wdok;
      {
        uint32_t n = 0;
        while (!(wdok = __all_sync(0xffffffffu, mbar_test(bar_box + (8 + (warp >> 1)) * 8, 0))) && !__all_sync(0xffffffffu, mbar_test(bar_sel, 0))) watchdog(n);
      }
      if (wdok) {
#pragma unroll
        for (int f = 0; f < 16; f++) LOAD_WD(f);
      }
      STAMP(11);
      mbar_wait(bar_sel, 0);
      PROF(8, ct == PT, 33); STAMP(12);
      float d[8][4];
#pragma unroll
      for (int i = 0; i < 4; i++) { d[i][0] = 0.f; d[i][1] = 0.f; d[i][2] = 0.f; d[i][3] = 0.f; }
#pragma unroll
      for (int ks = 0; ks < 8; ks++) {
        const uint2 hb = lds2(own + 256 + ks * 32 + tq * 8);
#pragma unroll
        for (int mt = 0; mt < 4; mt++) {
          const int r = ks * 16 + mt * 4;
          mma16816(d[mt], wf[r], wf[r + 1], wf[r + 2], wf[r + 3], hb.x, hb.y);
        }
      }
      sts2(own + (tq * 8 + g) * 8, __float_as_uint((tq & 2) ? ((tq & 1) ? d[1][2] : d[1][0]) : ((tq & 1) ? d[0][2] : d[0][0])),
           __float_as_uint((tq & 2) ? ((tq & 1) ? d[3][2] : d[3][0]) : ((tq & 1) ? d[2][2] : d[2][0])));
      bar_sync(1, 256);
      uint32_t ab[4];
      {
        float G = 0.f, U = 0.f;
        uint2 pv[8];
#pragma unroll
        for (int w8 = 0; w8 < 8; w8++) pv[w8] = lds2(base + ln * 8 + ((FT_G >> (w8 >> 1) * 4) & 15) * UNIT + (w8 & 1) * 8192);
#pragma unroll
        for (int w8 = 0; w8 < 8; w8 += 2) {
          G += __uint_as_float(pv[w8].x) + __uint_as_float(pv[w8 + 1].x);
          U += __uint_as_float(pv[w8].y) + __uint_as_float(pv[w8 + 1].y);
        }
        const float act = rbf(silu_f(rbf(G))) * rbf(U);
        const uint32_t pk = pack_bf(act, __shfl_down_sync(0xffffffffu, act, 1));
#pragma unroll
        for (int i = 0; i < 4; i++) ab[i] = __shfl_sync(0xffffffffu, pk, i * 8 + tq * 2);
      }
      if (!wdok) {
        mbar_wait(bar_box + (8 + (warp >> 1)) * 8, 0);
#pragma unroll
        for (int f = 0; f < 16; f++) LOAD_WD(f);
      }
      PROF(8, ct == PT, 34); STAMP(13);
#pragma unroll
      for (int mt = 0; mt < 8; mt++) {
        d[mt][0] = 0.f; d[mt][1] = 0.f; d[mt][2] = 0.f; d[mt][3] = 0.f;
        mma16816(d[mt], wd[mt * 8], wd[mt * 8 + 1], wd[mt * 8 + 2], wd[mt * 8 + 3], ab[0], ab[1]);
        mma16816(d[mt], wd[mt * 8 + 4], wd[mt * 8 + 5], wd[mt * 8 + 6], wd[mt * 8 + 7], ab[2], ab[3]);
      }
      uint32_t yw[4];
#pragma unroll
      for (int i = 0; i < 4; i++) yw[i] = (tq & 1) ? pack_bf(d[2 * i][2], d[2 * i + 1][2]) : pack_bf(d[2 * i][0], d[2 * i + 1][0]);
      if (tq < 2) st_b128(ydst, (yw[0] & ~1u) | (tag & 1), (yw[1] & ~1u) | (tag >> 1), yw[2], yw[3]);
      PROF(8, ct == PT, 35); STAMP(14);
    }
    mbar_wait(bar_sel, 0);
    mbar_arrive_pred(bar_win, ct == 0);
    const int iwin = lds1(par + PAR_CONST + 60) & 0x7ff;
    const bool cand = (iwin >> 4) == rb * 8 + warp;
    {
      const uint32_t mm0 = __shfl_sync(0xffffffffu, mm, ln & ~1), mm1 = __shfl_sync(0xffffffffu, mm, ln | 1);
      const uint32_t ih0 = __shfl_sync(0xffffffffu, ih, ln & ~1), ih1 = __shfl_sync(0xffffffffu, ih, ln | 1);
      const uint32_t il0 = __shfl_sync(0xffffffffu, il, ln & ~1), il1 = __shfl_sync(0xffffffffu, il, ln | 1);
#pragma unroll 1
      for (int hf = 0; hf < 2; hf++) {
        uint32_t x[16];
#pragma unroll
        for (int i = 0; i < 8; i += 2) ldmatrix4((trow ^ (i << 4)) + hf * 16384, x[2 * i], x[2 * i + 1], x[2 * i + 2], x[2 * i + 3]);
#pragma unroll
        for (int i = 0; i < 8; i++) {
          const uint4 pv = lds4(par + PAR_T2 + (hf * 8 + i) * 64 + tq * 16);
          x[2 * i] = hfma2(hfma2(ln_norm(x[2 * i], mm0, ih0, il0), pv.x, pv.y), pv.z, x[2 * i]);
          x[2 * i + 1] = hfma2(hfma2(ln_norm(x[2 * i + 1], mm1, ih1, il1), pv.x, pv.y), pv.z, x[2 * i + 1]);
        }
#pragma unroll
        for (int i = 0; i < 8; i += 2) stmatrix4((trow ^ (i << 4)) + hf * 16384, x[2 * i], x[2 * i + 1], x[2 * i + 2], x[2 * i + 3]);
        if (!cand) fence_async_smem();
        __syncwarp();
        if (!cand && elect_one()) {
          tma2d_store(&maps.out, res + hf * 16384 + warp * 2048, cj * 128 + hf * 64, rb * 128 + warp * 16);
          asm volatile("cp.async.bulk.commit_group;" ::: "memory");
        }
      }
    }
    if (cand) {
      const int wrow0 = warp * 16;
#pragma unroll 2
      for (int p = 0; p < 8; p++) {
        const int row = 2 * p + (ln >> 4), ch = ln & 15;
        const uint4 v = lds4(res + (ch >> 3) * 16384 + (wrow0 + row) * 128 + (((ch & 7) ^ (row & 7)) << 4));
        if (rb * 128 + wrow0 + row != iwin) *reinterpret_cast<uint4*>(P.out + (size_t)(rb * 128 + wrow0 + row) * DM + cj * 128 + ch * 8) = v;
      }
    }
    asm volatile("cp.async.bulk.wait_group.read 0;" ::: "memory");
    PROF(8, ct == PT, 11); STAMP(15);
    cluster_wait();
  }
}

typedef CUresult (*EncodeFn)(CUtensorMap*, CUtensorMapDataType, cuuint32_t, void*, const cuuint64_t*, const cuuint64_t*,
                             const cuuint32_t*, const cuuint32_t*, CUtensorMapInterleave, CUtensorMapSwizzle,
                             CUtensorMapL2promotion, CUtensorMapFloatOOBfill);

void map2d(EncodeFn enc, CUtensorMap* m, const void* p, uint64_t rows, uint64_t cols, uint32_t brows) {
  cuuint64_t dims[2] = {cols, rows}, strides[1] = {cols * 2};
  cuuint32_t box[2] = {64, brows}, es[2] = {1, 1};
  enc(m, CU_TENSOR_MAP_DATA_TYPE_BFLOAT16, 2, const_cast<void*>(p), dims, strides, box, es, CU_TENSOR_MAP_INTERLEAVE_NONE,
      CU_TENSOR_MAP_SWIZZLE_128B, CU_TENSOR_MAP_L2_PROMOTION_L2_256B, CU_TENSOR_MAP_FLOAT_OOB_FILL_NONE);
}
void map2d_narrow(EncodeFn enc, CUtensorMap* m, const void* p, uint64_t rows, uint64_t cols, uint32_t brows) {
  cuuint64_t dims[2] = {cols, rows}, strides[1] = {cols * 2};
  cuuint32_t box[2] = {32, brows}, es[2] = {1, 1};
  enc(m, CU_TENSOR_MAP_DATA_TYPE_BFLOAT16, 2, const_cast<void*>(p), dims, strides, box, es, CU_TENSOR_MAP_INTERLEAVE_NONE,
      CU_TENSOR_MAP_SWIZZLE_64B, CU_TENSOR_MAP_L2_PROMOTION_L2_64B, CU_TENSOR_MAP_FLOAT_OOB_FILL_NONE);
}
void map3d(EncodeFn enc, CUtensorMap* m, const void* p, uint64_t rows, uint64_t cols, uint32_t brows, uint32_t nch) {
  cuuint64_t dims[3] = {64, rows, cols / 64}, strides[2] = {cols * 2, 128};
  cuuint32_t box[3] = {64, brows, nch}, es[3] = {1, 1, 1};
  enc(m, CU_TENSOR_MAP_DATA_TYPE_BFLOAT16, 3, const_cast<void*>(p), dims, strides, box, es, CU_TENSOR_MAP_INTERLEAVE_NONE,
      CU_TENSOR_MAP_SWIZZLE_128B, CU_TENSOR_MAP_L2_PROMOTION_L2_256B, CU_TENSOR_MAP_FLOAT_OOB_FILL_NONE);
}

}

extern "C" void kernel_launch(void* const* d_in, const int* in_sizes, int n_in, void* d_out, int out_size) {
  (void)in_sizes; (void)n_in; (void)out_size;
  static EncodeFn enc = nullptr;
  if (!enc) {
    void* fn = nullptr;
    cudaDriverEntryPointQueryResult st;
    cudaGetDriverEntryPoint("cuTensorMapEncodeTiled", &fn, cudaEnableDefault, &st);
    enc = (EncodeFn)fn;
    cudaFuncSetAttribute(fused_kernel, cudaFuncAttributeMaxDynamicSharedMemorySize, SMEM_BYTES);
  }
  Maps maps;
  map2d(enc, &maps.x, d_in[0], SEQ, DM, 128);
  map2d(enc, &maps.out, d_out, SEQ, DM, 16);
  map3d(enc, &maps.wq, d_in[3], DM, NQ, 64, 2);
  map3d(enc, &maps.k, d_in[1], 4 * SK, 128, 128, 1);
  map3d(enc, &maps.v, d_in[2], 4 * SK, 128, 128, 1);
  map3d(enc, &maps.wo, d_in[4], NQ, DM, 64, 2);
  map2d_narrow(enc, &maps.wg, d_in[7], DM, FF, 256);
  map2d_narrow(enc, &maps.wu, d_in[8], DM, FF, 256);
  map3d(enc, &maps.wd, d_in[9], FF, DM, 32, 4);
  map2d_narrow(enc, &maps.wm, d_in[11], DM, NMOD, 256);
  Ptrs p;
  p.x = (const __nv_bfloat16*)d_in[0];
  p.w_r = (const __nv_bfloat16*)d_in[6];
  p.w_gate = (const __nv_bfloat16*)d_in[7];
  p.w_up = (const __nv_bfloat16*)d_in[8];
  p.w_down = (const __nv_bfloat16*)d_in[9];
  p.c = (const __nv_bfloat16*)d_in[10];
  p.w_mod = (const __nv_bfloat16*)d_in[11];
  p.out = (__nv_bfloat16*)d_out;
  fused_kernel<<<NMAIN + NHELP, 384, SMEM_BYTES>>>(maps, p);
}
```

```cpp
#include <cuda_runtime.h>
#include <cuda_bf16.h>
#include <cuda.h>
#include <stdint.h>
#include <type_traits>

#define HD 2
#define HDX 2
#define NRS 8
#define OSL 900
#define OSL2 400
#define VREL 5
#define OPS 8192
#define ODS1 5
#define ODS 8
#define PG0 15
#define WB 2
#define WN 20
#define HU 32
#define RES0 17
#define RES1 20
#define GOST 20
#define NS1 5
#define LD2 4
#define FPACE0 2
#define FPACE 3
#define CR 8
#define CS 8

namespace {

constexpr int SEQ = 2048, DM = 1024, NQ = 4096, SK = 2048, WIN = 512, FF = 3584, NMOD = 6144;
constexpr int NMAIN = 128, NHELP = 4, NFFN = 112;
constexpr int NSLOT = 4, SLOT_BYTES = 32768, UNIT = 16384, GST_BYTES = 3 * UNIT;
constexpr uint32_t XT1 = 0xDCBA, XT2 = 0x9687;
constexpr uint32_t WT0 = 0xA741, WT1 = 0x7420, WT2 = 0x4A20;
constexpr uint32_t AT0 = WT1, AT1 = WT2;
constexpr uint32_t QT = 0xDC9696DC;
constexpr int OFF_STAGE = 12 * UNIT;
constexpr uint32_t FT_G = 0x07B3, FT_U = 0xA628, FT_D = 0x5149;
constexpr int OFF_RES = 12 * UNIT;
constexpr int OFF_PAR = 14 * UNIT;
constexpr int OFF_BAR = OFF_PAR + 2528;
constexpr int SMEM_BYTES = OFF_BAR + 544;
static_assert(SMEM_BYTES <= 232448, "smem");

constexpr int PAR_T1 = 0;
constexpr int PAR_T2 = 512;
constexpr int PAR_CONST = 1536;
constexpr int PAR_RED = 1600;
constexpr int PAR_SINK = 2176;

struct Maps {
  CUtensorMap x, wq, k, v, wo, wg, wu, wd, wm, out;
};
struct Ptrs {
  const __nv_bfloat16 *x, *w_r, *c, *w_mod, *w_gate, *w_up, *w_down;
  __nv_bfloat16* out;
};

__device__ __align__(1024) uint8_t g_act[16 * 80 * UNIT];
__device__ __align__(128) uint32_t g_mod[NMOD];
__device__ __align__(128) uint32_t g_modp[2 * 2 * DM];
__device__ __align__(128) uint32_t g_ln1[SEQ * 4];
__device__ __align__(128) uint32_t g_cnt_h[16 * 32];
__device__ __align__(128) uint32_t g_cnt_o[128 * 32];
__device__ __align__(128) uint32_t g_xch[NMAIN * 8 * 256 * 4];
__device__ __align__(128) uint32_t g_stats[8 * SEQ * 4];
__device__ __align__(128) uint32_t g_cand[CR * 512];
__device__ __align__(128) uint32_t g_row[16 * 2 * DM];
__device__ __align__(128) uint32_t g_ypart[NMAIN * NFFN * 4];
__device__ __forceinline__ uint32_t* ypart_slot(int writer, int reader) { return g_ypart + (writer * NMAIN + reader) * 4; }
__device__ uint32_t g_epoch;

__device__ __forceinline__ uint32_t fresh_lane() { uint32_t l; asm volatile("mov.u32 %0, %%laneid;" : "=r"(l)); return l; }
__device__ __forceinline__ uint32_t frag_offset(int warp) {
  const uint32_t l = fresh_lane();
  return ((warp & 3) * 16 + (l & 15)) * 128 + (((l >> 4) ^ (l & 7)) << 4);
}
__device__ __forceinline__ bool elect_one() {
  uint32_t p;
  asm volatile("{ .reg .pred q; elect.sync _|q, 0xffffffff; selp.u32 %0, 1, 0, q; }" : "=r"(p));
  return p;
}
__device__ __forceinline__ uint32_t smem_u32(const void* p) { return (uint32_t)__cvta_generic_to_shared(p); }
__device__ __forceinline__ void mbar_init(uint32_t bar, uint32_t cnt) {
  asm volatile("mbarrier.init.shared::cta.b64 [%0], %1;" ::"r"(bar), "r"(cnt) : "memory");
}
__device__ __forceinline__ void mbar_expect_tx(uint32_t bar, uint32_t bytes) {
  asm volatile("mbarrier.arrive.expect_tx.shared::cta.b64 _, [%0], %1;" ::"r"(bar), "r"(bytes) : "memory");
}
__device__ __forceinline__ void mbar_arrive(uint32_t bar) {
  asm volatile("mbarrier.arrive.shared::cta.b64 _, [%0];" ::"r"(bar) : "memory");
}
__device__ __forceinline__ void mbar_arrive_pred(uint32_t bar, bool p) {
  asm volatile("{ .reg .pred p; setp.ne.b32 p, %1, 0; @p mbarrier.arrive.shared::cta.b64 _, [%0]; }" ::"r"(bar), "r"((int)p) : "memory");
}
__device__ __forceinline__ void mbar_arrive_cl(uint32_t bar, uint32_t off, bool p = true) {
  asm volatile("{ .reg .pred p, q; .reg .b32 a; setp.ne.b32 q, %2, 0; setp.ne.and.b32 p, %0, 0, q; add.u32 a, %0, %1; @p mbarrier.arrive.shared::cluster.b64 _, [a]; }"
               ::"r"(bar), "r"(off), "r"((int)p) : "memory");
}
__device__ __forceinline__ uint32_t mapa(uint32_t addr, uint32_t cta) {
  uint32_t r; asm("mapa.shared::cluster.u32 %0, %1, %2;" : "=r"(r) : "r"(addr), "r"(cta)); return r;
}
__device__ __forceinline__ void cluster_arrive() { asm volatile("barrier.cluster.arrive.relaxed.aligned;" ::: "memory"); }
__device__ __forceinline__ void cluster_wait() { asm volatile("barrier.cluster.wait.aligned;" ::: "memory"); }
__device__ __forceinline__ void watchdog(uint32_t& n) {
}
__device__ __forceinline__ void mbar_wait(uint32_t bar, uint32_t parity) {
  asm volatile("{\n.reg .pred p;\nWAIT_%=:\nmbarrier.try_wait.parity.shared::cta.b64 p, [%0], %1;\n@!p bra WAIT_%=;\n}" ::"r"(bar), "r"(parity) : "memory");
}
__device__ __forceinline__ bool mbar_test(uint32_t bar, uint32_t parity) {
  uint32_t ok;
  asm volatile("{\n.reg .pred p;\nmbarrier.test_wait.parity.shared::cta.b64 p, [%1], %2;\nselp.u32 %0, 1, 0, p;\n}" : "=r"(ok) : "r"(bar), "r"(parity) : "memory");
  return ok;
}
__device__ __forceinline__ uint64_t l2_stream() {
  uint64_t f; asm("createpolicy.fractional.L2::evict_first.b64 %0, 1.0;" : "=l"(f)); return f;
}
__device__ __forceinline__ void tma2d(uint32_t dst, const CUtensorMap* m, int c0, int c1, uint32_t bar) {
  asm volatile("cp.async.bulk.tensor.2d.shared::cluster.global.mbarrier::complete_tx::bytes.L2::cache_hint [%0], [%1, {%3, %4}], [%2], %5;"
               ::"r"(dst), "l"(m), "r"(bar), "r"(c0), "r"(c1), "l"(l2_stream()) : "memory");
}
__device__ __forceinline__ void bulk_load(uint32_t dst, const void* src, uint32_t bytes, uint32_t bar) {
  asm volatile("cp.async.bulk.shared::cluster.global.mbarrier::complete_tx::bytes [%0], [%1], %2, [%3];" ::"r"(dst), "l"(src), "r"(bytes), "r"(bar) : "memory");
}
__device__ __forceinline__ void bulk_load_stream(uint32_t dst, const void* src, uint32_t bytes, uint32_t bar) {
  asm volatile("cp.async.bulk.shared::cluster.global.mbarrier::complete_tx::bytes.L2::cache_hint [%0], [%1], %2, [%3], %4;"
               ::"r"(dst), "l"(src), "r"(bytes), "r"(bar), "l"(l2_stream()) : "memory");
}
__device__ __forceinline__ void tma2d_store(const CUtensorMap* m, uint32_t src, int c0, int c1) {
  asm volatile("cp.async.bulk.tensor.2d.global.shared::cta.bulk_group [%0, {%2, %3}], [%1];" ::"l"(m), "r"(src), "r"(c0), "r"(c1) : "memory");
}
__device__ __forceinline__ void bulk_store(void* dst, uint32_t src, uint32_t bytes) {
  asm volatile("cp.async.bulk.global.shared::cta.bulk_group [%0], [%1], %2;" ::"l"(dst), "r"(src), "r"(bytes) : "memory");
}
__device__ __forceinline__ int slice_of(int i) { return i + ((i & 7) == 1) - ((i & 7) == 2); }
__device__ __forceinline__ uint32_t unit_of(uint32_t table, uint32_t i) { return ((table >> (i * 4)) & 15) * UNIT; }
__device__ __forceinline__ void tma3d(uint32_t dst, const CUtensorMap* m, int c0, int c1, int c2, uint32_t bar) {
  asm volatile("cp.async.bulk.tensor.3d.shared::cluster.global.mbarrier::complete_tx::bytes.L2::cache_hint [%0], [%1, {%3, %4, %5}], [%2], %6;"
               ::"r"(dst), "l"(m), "r"(bar), "r"(c0), "r"(c1), "r"(c2), "l"(l2_stream()) : "memory");
}
template <bool STREAM>
__device__ __forceinline__ void tma3d_mc(uint32_t dst, const CUtensorMap* m, int c0, int c1, int c2, uint32_t bar) {
  if (STREAM)
    asm volatile("cp.async.bulk.tensor.3d.shared::cluster.global.mbarrier::complete_tx::bytes.multicast::cluster.L2::cache_hint [%0], [%1, {%3, %4, %5}], [%2], %6, %7;"
                 ::"r"(dst), "l"(m), "r"(bar), "r"(c0), "r"(c1), "r"(c2), "h"((uint16_t)3), "l"(l2_stream()) : "memory");
  else
    asm volatile("cp.async.bulk.tensor.3d.shared::cluster.global.mbarrier::complete_tx::bytes.multicast::cluster [%0], [%1, {%3, %4, %5}], [%2], %6;"
                 ::"r"(dst), "l"(m), "r"(bar), "r"(c0), "r"(c1), "r"(c2), "h"((uint16_t)3) : "memory");
}
__device__ __forceinline__ void prefetch_map(const CUtensorMap* m) {
  asm volatile("prefetch.tensormap [%0];" ::"l"(m) : "memory");
}
__device__ __forceinline__ void fence_async() { asm volatile("fence.proxy.async.global;" ::: "memory"); }
__device__ __forceinline__ void fence_async_smem() { asm volatile("fence.proxy.async.shared::cta;" ::: "memory"); }
__device__ __forceinline__ void bar_sync(int id, int n) { asm volatile("bar.sync %0, %1;" ::"r"(id), "r"(n) : "memory"); }
__device__ __forceinline__ void bar_arrive(int id, int n) { asm volatile("bar.arrive %0, %1;" ::"r"(id), "r"(n) : "memory"); }
__device__ __forceinline__ void wg_fence() { asm volatile("wgmma.fence.sync.aligned;" ::: "memory"); }
__device__ __forceinline__ void wg_commit() { asm volatile("wgmma.commit_group.sync.aligned;" ::: "memory"); }
template <int N> __device__ __forceinline__ void wg_wait() { asm volatile("wgmma.wait_group.sync.aligned %0;" ::"n"(N) : "memory"); }
__device__ __forceinline__ uint64_t make_desc(uint32_t addr, uint32_t lbo, uint32_t sbo) {
  return (uint64_t)((addr & 0x3FFFF) >> 4) | ((uint64_t)(lbo >> 4) << 16) | ((uint64_t)(sbo >> 4) << 32) | (1ull << 62);
}
__device__ __forceinline__ uint32_t ld_relaxed(const uint32_t* p) {
  uint32_t v; asm volatile("ld.relaxed.gpu.global.u32 %0, [%1];" : "=r"(v) : "l"(p) : "memory"); return v;
}
__device__ __forceinline__ uint32_t ld_acquire(const uint32_t* p) {
  uint32_t v; asm volatile("ld.acquire.gpu.global.u32 %0, [%1];" : "=r"(v) : "l"(p) : "memory"); return v;
}
__device__ __forceinline__ uint4 ld_relaxed4(const uint32_t* p) {
  uint4 v; asm volatile("ld.relaxed.gpu.global.v4.u32 {%0,%1,%2,%3}, [%4];" : "=r"(v.x), "=r"(v.y), "=r"(v.z), "=r"(v.w) : "l"(p) : "memory"); return v;
}
__device__ __forceinline__ void st_relaxed(uint32_t* p, uint32_t v) {
  asm volatile("st.relaxed.gpu.global.u32 [%0], %1;" ::"l"(p), "r"(v) : "memory");
}
__device__ __forceinline__ void st_relaxed4(uint32_t* p, uint32_t a, uint32_t b, uint32_t c, uint32_t d) {
  asm volatile("st.relaxed.gpu.global.v4.u32 [%0], {%1,%2,%3,%4};" ::"l"(p), "r"(a), "r"(b), "r"(c), "r"(d) : "memory");
}
__device__ __forceinline__ void st_b128(uint32_t* p, uint32_t a, uint32_t b, uint32_t c, uint32_t d) {
  asm volatile("{ .reg .b64 u, v; .reg .b128 w; mov.b64 u, {%1, %2}; mov.b64 v, {%3, %4}; mov.b128 w, {u, v}; st.relaxed.gpu.global.b128 [%0], w; }"
               ::"l"(p), "r"(a), "r"(b), "r"(c), "r"(d) : "memory");
}
__device__ __forceinline__ uint4 ld_b128(const uint32_t* p) {
  uint4 r;
  asm volatile("{ .reg .b64 u, v; .reg .b128 w; ld.relaxed.gpu.global.b128 w, [%4]; mov.b128 {u, v}, w; mov.b64 {%0, %1}, u; mov.b64 {%2, %3}, v; }"
               : "=r"(r.x), "=r"(r.y), "=r"(r.z), "=r"(r.w) : "l"(p) : "memory");
  return r;
}
__device__ __forceinline__ void st_pairs(uint32_t* p, uint32_t a, uint32_t b, uint32_t tag) {
  asm volatile("{ .reg .b64 u, v; mov.b64 u, {%1, %3}; mov.b64 v, {%2, %3}; st.relaxed.gpu.global.v2.b64 [%0], {u, v}; }"
               ::"l"(p), "r"(a), "r"(b), "r"(tag) : "memory");
}
__device__ __forceinline__ uint4 ld_pairs(const uint32_t* p) {
  uint4 v;
  asm volatile("{ .reg .b64 u, v; ld.relaxed.gpu.global.v2.b64 {u, v}, [%4]; mov.b64 {%0, %1}, u; mov.b64 {%2, %3}, v; }"
               : "=r"(v.x), "=r"(v.y), "=r"(v.z), "=r"(v.w) : "l"(p) : "memory");
  return v;
}
__device__ __forceinline__ uint2 ld_pair(const uint32_t* p) {
  uint2 v;
  asm volatile("{ .reg .b64 u; ld.relaxed.gpu.global.b64 u, [%2]; mov.b64 {%0, %1}, u; }" : "=r"(v.x), "=r"(v.y) : "l"(p) : "memory");
  return v;
}
__device__ __forceinline__ void red_release(uint32_t* p, uint32_t v) {
  asm volatile("red.release.gpu.global.add.u32 [%0], %1;" ::"l"(p), "r"(v) : "memory");
}
__device__ __forceinline__ uint32_t ldg_nc1(const void* p) {
  uint32_t v;
  asm volatile("ld.global.nc.u32 %0, [%1];" : "=r"(v) : "l"(p));
  return v;
}
__device__ __forceinline__ uint4 ldg_nc4(const void* p) {
  uint4 v; asm volatile("ld.global.nc.L1::no_allocate.v4.u32 {%0,%1,%2,%3}, [%4];" : "=r"(v.x), "=r"(v.y), "=r"(v.z), "=r"(v.w) : "l"(p)); return v;
}
__device__ __forceinline__ uint4 ldg_stream4(const void* p) {
  uint4 v;
  asm volatile("ld.global.nc.L1::no_allocate.L2::cache_hint.v4.u32 {%0,%1,%2,%3}, [%4], %5;" : "=r"(v.x), "=r"(v.y), "=r"(v.z), "=r"(v.w) : "l"(p), "l"(l2_stream()));
  return v;
}
__device__ __forceinline__ void stg4(void* p, uint4 v) {
  asm volatile("st.global.v4.u32 [%0], {%1,%2,%3,%4};" ::"l"(p), "r"(v.x), "r"(v.y), "r"(v.z), "r"(v.w) : "memory");
}
__device__ __forceinline__ void wait_counter(const uint32_t* p, uint32_t target) {
  uint32_t n = 0;
  while (__any_sync(0xffffffffu, (int)(ld_acquire(p) - target) < 0)) { watchdog(n); }
}
__device__ __forceinline__ uint32_t tagf(float v, uint32_t tag) { return (__float_as_uint(v) & ~3u) | tag; }
__device__ __forceinline__ bool tag_ok(uint4 v, uint32_t tag) { return (((v.x ^ tag) | (v.y ^ tag) | (v.z ^ tag) | (v.w ^ tag)) & 3u) == 0; }
__device__ __forceinline__ float untag_sum(uint32_t a, uint32_t b) { return __uint_as_float(a & ~3u) + __uint_as_float(b & ~3u); }
__device__ __forceinline__ uint4 poll4(const uint32_t* p, uint32_t tag) {
  uint4 v = ld_relaxed4(p);
  uint32_t n = 0;
  while (!__all_sync(0xffffffffu, tag_ok(v, tag))) { v = ld_relaxed4(p); watchdog(n); }
  return v;
}
__device__ __forceinline__ float bf_lo(uint32_t v) { return __uint_as_float(v << 16); }
__device__ __forceinline__ float bf_hi(uint32_t v) { return __uint_as_float(v & 0xffff0000u); }
__device__ __forceinline__ uint32_t pack_bf(float lo, float hi) {
  uint32_t r; asm("cvt.rn.bf16x2.f32 %0, %1, %2;" : "=r"(r) : "f"(hi), "f"(lo)); return r;
}
__device__ __forceinline__ float rbf(float v) { return __uint_as_float(pack_bf(0.f, v) & 0xffff0000u); }
__device__ __forceinline__ uint32_t hmul2(uint32_t a, uint32_t b) {
  uint32_t r; asm("mul.rn.bf16x2 %0, %1, %2;" : "=r"(r) : "r"(a), "r"(b)); return r;
}
__device__ __forceinline__ uint32_t hadd2(uint32_t a, uint32_t b) {
  uint32_t r; asm("add.rn.bf16x2 %0, %1, %2;" : "=r"(r) : "r"(a), "r"(b)); return r;
}
__device__ __forceinline__ uint32_t hsub2(uint32_t a, uint32_t b) {
  uint32_t r; asm("sub.rn.bf16x2 %0, %1, %2;" : "=r"(r) : "r"(a), "r"(b)); return r;
}
__device__ __forceinline__ float rcp(float x) { float r; asm("rcp.approx.ftz.f32 %0, %1;" : "=f"(r) : "f"(x)); return r; }
__device__ __forceinline__ float ex2(float x) { float r; asm("ex2.approx.ftz.f32 %0, %1;" : "=f"(r) : "f"(x)); return r; }
__device__ __forceinline__ void stmatrix4(uint32_t addr, uint32_t a, uint32_t b, uint32_t c, uint32_t d) {
  asm volatile("stmatrix.sync.aligned.m8n8.x4.shared.b16 [%0], {%1,%2,%3,%4};" ::"r"(addr), "r"(a), "r"(b), "r"(c), "r"(d) : "memory");
}
__device__ __forceinline__ void ldmatrix4(uint32_t addr, uint32_t& a, uint32_t& b, uint32_t& c, uint32_t& d) {
  asm volatile("ldmatrix.sync.aligned.m8n8.x4.shared.b16 {%0,%1,%2,%3}, [%4];" : "=r"(a), "=r"(b), "=r"(c), "=r"(d) : "r"(addr) : "memory");
}
__device__ __forceinline__ void ldmatrix4t(uint32_t addr, uint32_t& a, uint32_t& b, uint32_t& c, uint32_t& d) {
  asm volatile("ldmatrix.sync.aligned.m8n8.x4.trans.shared.b16 {%0,%1,%2,%3}, [%4];" : "=r"(a), "=r"(b), "=r"(c), "=r"(d) : "r"(addr) : "memory");
}
__device__ __forceinline__ void mma16816(float (&d)[4], uint32_t a0, uint32_t a1, uint32_t a2, uint32_t a3, uint32_t b0, uint32_t b1) {
  asm volatile("mma.sync.aligned.m16n8k16.row.col.f32.bf16.bf16.f32 {%0,%1,%2,%3}, {%4,%5,%6,%7}, {%8,%9}, {%0,%1,%2,%3};"
               : "+f"(d[0]), "+f"(d[1]), "+f"(d[2]), "+f"(d[3]) : "r"(a0), "r"(a1), "r"(a2), "r"(a3), "r"(b0), "r"(b1));
}
__device__ __forceinline__ void sts1(uint32_t a, uint32_t v) { asm volatile("st.shared.u32 [%0], %1;" ::"r"(a), "r"(v) : "memory"); }
__device__ __forceinline__ uint4 lds4(uint32_t a) {
  uint4 v; asm volatile("ld.shared.v4.u32 {%0,%1,%2,%3}, [%4];" : "=r"(v.x), "=r"(v.y), "=r"(v.z), "=r"(v.w) : "r"(a) : "memory"); return v;
}
__device__ __forceinline__ uint2 lds2(uint32_t a) {
  uint2 v; asm volatile("ld.shared.v2.u32 {%0,%1}, [%2];" : "=r"(v.x), "=r"(v.y) : "r"(a) : "memory"); return v;
}
__device__ __forceinline__ uint32_t lds1(uint32_t a) {
  uint32_t v; asm volatile("ld.shared.u32 %0, [%1];" : "=r"(v) : "r"(a) : "memory"); return v;
}
__device__ __forceinline__ void sts2(uint32_t a, uint32_t x, uint32_t y) { asm volatile("st.shared.v2.u32 [%0], {%1,%2};" ::"r"(a), "r"(x), "r"(y) : "memory"); }
__device__ __forceinline__ void sts4(uint32_t a, uint4 v) {
  asm volatile("st.shared.v4.u32 [%0], {%1,%2,%3,%4};" ::"r"(a), "r"(v.x), "r"(v.y), "r"(v.z), "r"(v.w) : "memory");
}
__device__ __forceinline__ float silu_f(float v) { return __fdividef(v, 1.f + __expf(-v)); }
__device__ __forceinline__ uint32_t hfma2(uint32_t a, uint32_t b, uint32_t c) {
  uint32_t r; asm("fma.rn.bf16x2 %0, %1, %2, %3;" : "=r"(r) : "r"(a), "r"(b), "r"(c)); return r;
}
__device__ __forceinline__ void split_inv(float sd, uint32_t& ih, uint32_t& il) {
  const float inv = rcp(sd);
  ih = pack_bf(inv, inv);
  const float lo = inv - bf_lo(ih);
  il = pack_bf(lo, lo);
}
__device__ __forceinline__ uint32_t ln_norm(uint32_t x, uint32_t mean2, uint32_t ih, uint32_t il) {
  const uint32_t d = hsub2(x, mean2);
  return hfma2(d, ih, hmul2(d, il));
}
__device__ __forceinline__ uint32_t ln_mod(uint32_t x, uint32_t mean2, uint32_t ih, uint32_t il, uint32_t c1, uint32_t sh) {
  return hadd2(hmul2(ln_norm(x, mean2, ih, il), c1), sh);
}

#define R8(a, i) "+f"(a[i]), "+f"(a[i + 1]), "+f"(a[i + 2]), "+f"(a[i + 3]), "+f"(a[i + 4]), "+f"(a[i + 5]), "+f"(a[i + 6]), "+f"(a[i + 7])
#define D64 "{%0,%1,%2,%3,%4,%5,%6,%7,%8,%9,%10,%11,%12,%13,%14,%15,%16,%17,%18,%19,%20,%21,%22,%23,%24,%25,%26,%27,%28,%29,%30,%31," \
            "%32,%33,%34,%35,%36,%37,%38,%39,%40,%41,%42,%43,%44,%45,%46,%47,%48,%49,%50,%51,%52,%53,%54,%55,%56,%57,%58,%59,%60,%61,%62,%63}"
template <int TB>
__device__ __forceinline__ void mma_ss(float (&d)[64], uint64_t da, uint64_t db, int sc) {
  asm volatile("{\n.reg .pred p;\nsetp.ne.b32 p, %66, 0;\n"
               "wgmma.mma_async.sync.aligned.m64n128k16.f32.bf16.bf16 " D64 ", %64, %65, p, 1, 1, 0, %67;\n}"
               : R8(d, 0), R8(d, 8), R8(d, 16), R8(d, 24), R8(d, 32), R8(d, 40), R8(d, 48), R8(d, 56)
               : "l"(da), "l"(db), "r"(sc), "n"(TB));
}
template <int TB>
__device__ __forceinline__ void mma_rs(float (&d)[64], uint32_t a0, uint32_t a1, uint32_t a2, uint32_t a3, uint64_t db, int sc) {
  asm volatile("{\n.reg .pred p;\nsetp.ne.b32 p, %69, 0;\n"
               "wgmma.mma_async.sync.aligned.m64n128k16.f32.bf16.bf16 " D64 ", {%64,%65,%66,%67}, %68, p, 1, 1, %70;\n}"
               : R8(d, 0), R8(d, 8), R8(d, 16), R8(d, 24), R8(d, 32), R8(d, 40), R8(d, 48), R8(d, 56)
               : "r"(a0), "r"(a1), "r"(a2), "r"(a3), "l"(db), "r"(sc), "n"(TB));
}
#define D128 "{%0,%1,%2,%3,%4,%5,%6,%7,%8,%9,%10,%11,%12,%13,%14,%15,%16,%17,%18,%19,%20,%21,%22,%23,%24,%25,%26,%27,%28,%29,%30,%31," \
             "%32,%33,%34,%35,%36,%37,%38,%39,%40,%41,%42,%43,%44,%45,%46,%47,%48,%49,%50,%51,%52,%53,%54,%55,%56,%57,%58,%59,%60,%61,%62,%63," \
             "%64,%65,%66,%67,%68,%69,%70,%71,%72,%73,%74,%75,%76,%77,%78,%79,%80,%81,%82,%83,%84,%85,%86,%87,%88,%89,%90,%91,%92,%93,%94,%95," \
             "%96,%97,%98,%99,%100,%101,%102,%103,%104,%105,%106,%107,%108,%109,%110,%111,%112,%113,%114,%115,%116,%117,%118,%119,%120,%121,%122,%123,%124,%125,%126,%127}"
#define R128(d, e) R8(d, 0), R8(d, 8), R8(d, 16), R8(d, 24), R8(d, 32), R8(d, 40), R8(d, 48), R8(d, 56), \
                   R8(e, 0), R8(e, 8), R8(e, 16), R8(e, 24), R8(e, 32), R8(e, 40), R8(e, 48), R8(e, 56)
__device__ __forceinline__ void mma256_ss(float (&d)[64], float (&e)[64], uint64_t da, uint64_t db, int sc) {
  asm volatile("{\n.reg .pred p;\nsetp.ne.b32 p, %130, 0;\n"
               "wgmma.mma_async.sync.aligned.m64n256k16.f32.bf16.bf16 " D128 ", %128, %129, p, 1, 1, 0, 1;\n}"
               : R128(d, e) : "l"(da), "l"(db), "r"(sc));
}
__device__ __forceinline__ void mma256_rs(float (&d)[64], float (&e)[64], uint32_t a0, uint32_t a1, uint32_t a2, uint32_t a3, uint64_t db) {
  asm volatile("{\n.reg .pred p;\nsetp.ne.b32 p, 1, 0;\n"
               "wgmma.mma_async.sync.aligned.m64n256k16.f32.bf16.bf16 " D128 ", {%128,%129,%130,%131}, %132, p, 1, 1, 1;\n}"
               : R128(d, e) : "r"(a0), "r"(a1), "r"(a2), "r"(a3), "l"(db));
}
template <int N> __device__ __forceinline__ void keep(float (&a)[N]) {
#pragma unroll
  for (int i = 0; i < N; i++) asm volatile("" : "+f"(a[i])::"memory");
}
template <int N> __device__ __forceinline__ void keep(uint32_t (&a)[N]) {
#pragma unroll
  for (int i = 0; i < N; i++) asm volatile("" : "+r"(a[i])::"memory");
}

#define STAMP(idx) do {} while (0)
#define PROF(grp, cond, idx) do {} while (0)

constexpr float SCL2 = 1.4426950408889634f * 0.08838834764831845f;

__device__ __forceinline__ void pack_p(const float (&s)[64], uint32_t (&p)[32]) {
#pragma unroll
  for (int i = 0; i < 32; i++) p[i] = pack_bf(s[2 * i], s[2 * i + 1]);
}

__device__ __forceinline__ void issue_qk(float (&s)[64], uint32_t q0, uint32_t q1, uint32_t kslot) {
  const uint64_t db = make_desc(kslot, 16, 1024), da0 = make_desc(q0, 16, 1024), da1 = make_desc(q1, 16, 1024);
#pragma unroll
  for (int kk = 0; kk < 8; kk++) mma_ss<0>(s, (kk < 4 ? da0 : da1) + (kk & 3) * 2, db + (kk >> 2) * 1024 + (kk & 3) * 2, kk != 0);
}
__device__ __forceinline__ void issue_pv(float (&o)[64], uint32_t (&p)[32], uint32_t vslot, int acc) {
  uint64_t db = make_desc(vslot, 16384, 1024);
#pragma unroll
  for (int kk = 0; kk < 8; kk++)
    mma_rs<1>(o, p[4 * kk], p[4 * kk + 1], p[4 * kk + 2], p[4 * kk + 3], db + kk * 128, kk == 0 ? acc : 1);
}

template <int H>
__device__ __forceinline__ void store_chunk(const float (&a)[64], uint32_t addr) {
#pragma unroll
  for (int i = 8 * H; i < 8 * H + 8; i += 2)
    stmatrix4(addr ^ ((i & 7) << 4), pack_bf(a[4 * i], a[4 * i + 1]), pack_bf(a[4 * i + 2], a[4 * i + 3]),
              pack_bf(a[4 * i + 4], a[4 * i + 5]), pack_bf(a[4 * i + 6], a[4 * i + 7]));
}
template <int H>
__device__ __forceinline__ void store_chunk(const float (&a)[64], float i0, float i1, uint32_t addr) {
#pragma unroll
  for (int i = 8 * H; i < 8 * H + 8; i += 2)
    stmatrix4(addr ^ ((i & 7) << 4), pack_bf(a[4 * i] * i0, a[4 * i + 1] * i0), pack_bf(a[4 * i + 2] * i1, a[4 * i + 3] * i1),
              pack_bf(a[4 * i + 4] * i0, a[4 * i + 5] * i0), pack_bf(a[4 * i + 6] * i1, a[4 * i + 7] * i1));
}
__device__ __forceinline__ float inv_quad_sum(float l) {
  l += __shfl_xor_sync(0xffffffffu, l, 1);
  l += __shfl_xor_sync(0xffffffffu, l, 2);
  return rcp(l);
}

__device__ __forceinline__ void write_table(uint32_t table, bool ca, uint32_t t, const uint4& m0, const uint4& m1) {
  float c0 = untag_sum(m0.x, m1.x), c1 = untag_sum(m0.y, m1.y), c2 = untag_sum(m0.z, m1.z), c3 = untag_sum(m0.w, m1.w);
  if (ca) { c0 = 1.f + rbf(c0); c1 = 1.f + rbf(c1); c2 = 1.f + rbf(c2); c3 = 1.f + rbf(c3); }
  const uint32_t d = table + (t >> 2) * 64 + (t & 1) * 32 + (t & 2) * 2 + (ca ? 0 : 8);
  sts1(d, pack_bf(c0, c1));
  sts1(d + 16, pack_bf(c2, c3));
}

__device__ __forceinline__ void ln_scalars(float mean, float var, float& mb, float& sd) {
  mb = rbf(mean);
  float r; asm("sqrt.approx.ftz.f32 %0, %1;" : "=f"(r) : "f"(rbf(rbf(var) + 1e-5f)));
  sd = rbf(r);
}

__global__ void __cluster_dims__(2, 1, 1) __launch_bounds__(384, 1) fused_kernel(const __grid_constant__ Maps maps, const Ptrs P) {
  extern __shared__ __align__(1024) uint8_t smem_raw[];
  const uint32_t base = smem_u32(smem_raw);
  const int tid = threadIdx.x, lane = tid & 31;
  const int warp = __shfl_sync(0xffffffffu, tid >> 5, 0);
  const int b = blockIdx.x;
  PROF(31, tid == 0, 0);

  if (b >= NMAIN) {
    float* sc = reinterpret_cast<float*>(smem_raw);
    float* red = sc + DM;
    for (int k = tid; k < DM; k += 384) sc[k] = rbf(silu_f(__bfloat162float(P.c[k])));
    __syncthreads();
    if (tid < 256) {
      const int col = 2048 + (b - NMAIN) * 1024 + (tid & 127) * 8, r0 = (tid >> 7) * 512;
      float acc[8];
#pragma unroll
      for (int e = 0; e < 8; e++) acc[e] = 0.f;
#pragma unroll 1
      for (int r = r0; r < r0 + 512; r += HU) {
        uint4 w[HU];
#pragma unroll
        for (int u = 0; u < HU; u++) w[u] = ldg_stream4(P.w_mod + (size_t)(r + u) * NMOD + col);
#pragma unroll
        for (int u = 0; u < HU; u++) {
          float s = sc[r + u];
          acc[0] += s * bf_lo(w[u].x); acc[1] += s * bf_hi(w[u].x); acc[2] += s * bf_lo(w[u].y); acc[3] += s * bf_hi(w[u].y);
          acc[4] += s * bf_lo(w[u].z); acc[5] += s * bf_hi(w[u].z); acc[6] += s * bf_lo(w[u].w); acc[7] += s * bf_hi(w[u].w);
        }
      }
      if (tid >= 128) {
#pragma unroll
        for (int e = 0; e < 8; e++) red[(tid & 127) * 8 + e] = acc[e];
      }
      const uint32_t tag = ld_relaxed(&g_epoch) % 3 + 1;
      bar_sync(1, 256);
      if (tid < 128) {
        uint32_t o[8];
#pragma unroll
        for (int e = 0; e < 8; e++) o[e] = __float_as_uint(rbf(acc[e] + red[tid * 8 + e])) | tag;
        st_relaxed4(g_mod + col, o[0], o[1], o[2], o[3]);
        st_relaxed4(g_mod + col + 4, o[4], o[5], o[6], o[7]);
        const uint4 wr = ldg_nc4(P.w_r + tid * 8);
        const uint32_t wv[4] = {wr.x, wr.y, wr.z, wr.w};
        float dsum = 0.f;
#pragma unroll
        for (int e = 0; e < 8; e++) {
          const float m = bf_hi(o[e]);
          dsum += (b == NMAIN + 2 ? rbf(1.f + m) : m) * ((e & 1) ? bf_hi(wv[e >> 1]) : bf_lo(wv[e >> 1]));
        }
#pragma unroll
        for (int k = 16; k > 0; k >>= 1) dsum += __shfl_xor_sync(0xffffffffu, dsum, k);
        if (lane == 0) st_relaxed(g_mod + (b - NMAIN) * 4 + warp, tagf(dsum, tag));
      }
    }
    PROF(2, tid == 0, 1);
    return;
  }

  const int rank = b & 1;
  const int rb = ((b >> 4) << 1) | rank, cj = (b >> 1) & 7;
  const bool late = b & 4;
  const uint32_t bfull = base + OFF_BAR, bempty = bfull + NSLOT * 8;
  const uint32_t gfull = bempty + NSLOT * 8, gempty = gfull + 32;
  const uint32_t bar_ofull = gempty + 32;
  const uint32_t bar_ofree = bar_ofull + 32;
  const uint32_t bar_par = bar_ofree + 32;
  const uint32_t bar_mod = bar_par + 8;
  const uint32_t bar_pread = bar_mod + 8;
  const uint32_t bar_xres = bar_pread + 8;
  const uint32_t bar_ring = bar_xres + 8;
  const uint32_t bar_box = bar_ring + 24;
  const uint32_t bar_go = bar_box + 96;
  const uint32_t bar_go2 = bar_go + 16;
  const uint32_t bar_cnt = bar_go + 24;
  const uint32_t xfull = bar_go + 40, xempty = xfull + 32;
  const uint32_t bar_hw = xempty + 32, bar_hx = bar_hw + 8;
  const uint32_t bar_hpub = bar_hx + 16;
  const uint32_t bar_win = bar_hpub + 16;
  const uint32_t bar_rx = bar_win + 8;
  const uint32_t bar_sel = bar_rx + 8;
  const uint32_t bar_gate = bar_sel + 8;
  const uint32_t bar_rel = bar_gate + 8;
  const uint32_t bar_od = bar_rel + 8;
  const uint32_t bar_mod2 = bar_od + 8;
  const uint32_t bar_res = bar_go + 8;
  const uint32_t stage = base + OFF_STAGE, par = base + OFF_PAR;

  if (warp == 10 && elect_one()) prefetch_map(&maps.wm);
  if (warp == 8 && elect_one()) {
    for (int s = 0; s < NSLOT; s++) { mbar_init(bfull + s * 8, 1); mbar_init(bempty + s * 8, 16); }
    for (int s = 0; s < 4; s++) { mbar_init(gfull + s * 8, 1); mbar_init(gempty + s * 8, 16); mbar_init(xfull + s * 8, 1); mbar_init(xempty + s * 8, 8); mbar_init(bar_ofree + s * 8, 1); mbar_init(bar_ofull + s * 8, 128); }
    mbar_init(bar_par, 64); mbar_init(bar_mod, 256); mbar_init(bar_pread, 2); mbar_init(bar_xres, 1);
    mbar_init(bar_ring, 8); mbar_init(bar_ring + 8, 8); mbar_init(bar_ring + 16, 8);
    mbar_init(bar_go, 1); mbar_init(bar_go2, 1); mbar_init(bar_cnt, 1); mbar_init(bar_cnt + 8, 1); mbar_init(bar_hpub, 8); mbar_init(bar_hpub + 8, 8); mbar_init(bar_res, 1); mbar_init(bar_win, 1); mbar_init(bar_rx, 1); mbar_init(bar_sel, 64); mbar_init(bar_gate, 8); mbar_init(bar_rel, 8); mbar_init(bar_od, 1); mbar_init(bar_mod2, 64);
    for (int s = 0; s < 12; s++) mbar_init(bar_box + s * 8, 1);
    asm volatile("fence.mbarrier_init.release.cluster;" ::: "memory");
    prefetch_map(&maps.x); prefetch_map(&maps.wq); prefetch_map(&maps.k); prefetch_map(&maps.v);
  }
  if (warp == 9 && elect_one()) {
    mbar_init(bar_hw, 1); mbar_init(bar_hx, 1); mbar_init(bar_hx + 8, 1);
    asm volatile("fence.mbarrier_init.release.cluster;" ::: "memory");
    mbar_expect_tx(bar_hw, 32768);
    mbar_expect_tx(bar_hx, 16384);
    mbar_expect_tx(bar_hx + 8, 16384);
    const __nv_bfloat16* xs = P.x + (size_t)(rb * 128 + cj * 16) * DM;
    bulk_load(base + 2 * GST_BYTES, xs, 16384, bar_hx);
    if (!late) {
      tma2d(stage, &maps.wm, (b >> 1) * 32, rank * 512, bar_hw);
      tma2d(stage + 16384, &maps.wm, (b >> 1) * 32, rank * 512 + 256, bar_hw);
    }
    bulk_load(base + 3 * GST_BYTES, xs + 8 * DM, 16384, bar_hx + 8);
  }
  cluster_arrive();

  if (warp >= 8) {
    asm volatile("setmaxnreg.dec.sync.aligned.u32 40;");
    if (warp < 10) bar_arrive(1, 320);
    const uint32_t epoch = ld_relaxed(&g_epoch);
    cluster_wait();
    if (warp == 8) {
      const int kvrow = (cj >> 1) * SK + (SK - WIN);
      int wch = cj * 8 + rank * 2;
#pragma unroll 1
      for (int ps = 0; ps < 3; ps++) {
        const CUtensorMap* mw = ps == 2 ? &maps.wo : &maps.wq;
        const uint32_t xt = ps == 1 ? XT1 : XT2, wt = ps == 0 ? WT0 : (ps == 1 ? WT1 : WT2);
        const int nst = ps == 2 ? 32 : 16;
#pragma unroll 1
        for (int i = 0; i < nst; i++) {
          const uint32_t bf = gfull + (i & 3) * 8;
          const int kt = ps == 2 ? (((cj & 1) * 4 + ((i >> 1) & 3)) * 4 + (i >> 3)) * 2 + (i & 1) : (ps ? i : slice_of(i) + (b & 14)) & 15;
          const uint32_t wd = base + unit_of(wt, i & 3) + rank * UNIT, xd = base + unit_of(xt, i & 3);
          const uint8_t* xs = g_act + (uint32_t)(rb * 80 + (ps - 1) * 16 + kt) * UNIT;
          if (ps == 0 && i == HD) mbar_wait(bar_mod, 0);
          const bool xfirst = ps && i < 2;
          if (ps == 2 && i == 0) mbar_wait(bar_ofree + 24, 0);
          if (i == 0) fence_async();
          mbar_wait(gempty + (i & 3) * 8, ((i >> 2) & 1) ^ 1);
          if (elect_one()) {
            mbar_expect_tx(bf, ps ? GST_BYTES : 2 * UNIT);
            if (xfirst) bulk_load_stream(xd, xs, UNIT, bf);
          }
          if (ps && i < 4) mbar_wait(bempty + i * 8, 1);
          if (elect_one()) tma3d_mc<true>(wd, mw, 0, (i == 31 ? kt ^ (rank * 32) : kt) * 64, i == 31 ? cj * 2 : wch, bf);
          if (ps) {
            if (i == 16 || i == 24) { mbar_wait(bar_cnt + i - 16, 0); fence_async(); }
            if (i == RES0) mbar_wait(bar_res, 0);
            if (i == 2) mbar_wait(bar_ofree + (ps - 1) * 16, 0);
            if (elect_one()) {
              if (i == 31) bulk_load(xd, xs, UNIT, bf); else if (!xfirst) bulk_load_stream(xd, xs, UNIT, bf);
              mbar_arrive_pred(bar_go, i == GOST - 1);
              mbar_arrive_pred(bar_go2, ps == 1 && i == PG0);
              mbar_arrive_pred(bar_od, i == (ps == 1 ? ODS1 : ODS));
              if (i == RES0) mbar_expect_tx(bar_xres, 32768);
              if (i == RES0 || i == RES1) tma2d(base + OFF_RES + (i == RES1) * UNIT, &maps.x, cj * 128 + (i == RES1) * 64, rb * 128, bar_xres);
            }
          }
        }
        if (ps == 2) break;
        wch = ps ? ((wch >> 3) ^ rank) * 2 : wch + 4;
#pragma unroll 1
        for (int u = 0; u < 16; u++) {
          const bool isk = (u == 0) || ((u & 1) && u < 15);
          const int blk = (isk ? (u + 1) >> 1 : (u == 15 ? 7 : (u >> 1) - 1)) & 3;
          const uint32_t sl = base + unit_of(ps ? AT1 : AT0, u & 3) + rank * UNIT, bf = bfull + (u & 3) * 8;
          if (u < 4) mbar_wait(gempty + ((u + 1) >> 1) * 8, 1);
          mbar_wait(bempty + (u & 3) * 8, ((u >> 2) & 1) ^ 1);
          if (elect_one()) {
            mbar_expect_tx(bf, SLOT_BYTES);
            if (ps && u >= 7 && u != 8) tma3d_mc<true>(sl, isk ? &maps.k : &maps.v, 0, kvrow + blk * 128, rank, bf);
            else tma3d_mc<false>(sl, isk ? &maps.k : &maps.v, 0, kvrow + blk * 128, rank, bf);
          }
        }
      }
      if (elect_one()) mbar_expect_tx(bar_rx, UNIT);
      mbar_wait(bar_rel, 0);
      if (elect_one()) {
        bulk_load_stream(base + UNIT, g_act + (uint32_t)(rb * 80 + 16 + 63 - (cj & 1) * 32) * UNIT, UNIT, bar_rx);
      }
      if (b < NFFN) {
#pragma unroll 1
        for (int u = 0; u < 12; u++) {
          const uint32_t dst = base + unit_of(u < 4 ? FT_G : (u < 8 ? FT_U : FT_D), u & 3);
          if (elect_one()) mbar_expect_tx(bar_box + u * 8, UNIT);
          if (u == 0 || u == 2 || u == 8) mbar_wait(bar_ring + (u == 8 ? 16 : u * 4), 0);
          const int fp = u < 8 ? FPACE0 : FPACE;
          if (u >= fp) mbar_wait(bar_box + (u - fp) * 8, 0);
          if (elect_one()) {
            if (u < 8) tma2d(dst, u < 4 ? &maps.wg : &maps.wu, b * 32, (u & 3) * 256, bar_box + u * 8);
            else tma3d(dst, &maps.wd, 0, b * 32, (u - 8) * 4, bar_box + u * 8);
          }
        }
      }
    } else if (warp == 9) {
      const uint32_t target = 8 * (epoch + 1);
      uint32_t hmask = 0;
#pragma unroll 1
      for (int i = 0; i < 16; i++) {
        if (i == HDX) mbar_wait(bar_mod, 0);
        const int kt = (2 * cj + slice_of(i)) & 15;
        const uint32_t need = i == 15 ? 0xffffu : 1u << kt;
        if (i >= NRS && (hmask & need) != need) {
          uint32_t n = 0;
          do { hmask = __ballot_sync(0xffffffffu, ld_acquire(&g_cnt_h[rb * 32 + (lane & 15)]) == epoch + 1); watchdog(n); } while ((hmask & need) != need);
          PROF(1, lane == 0 && i == NRS, 26);
          fence_async();
        }
        mbar_wait(xempty + (i & 3) * 8, ((i >> 2) & 1) ^ 1);
        if (elect_one()) {
          mbar_expect_tx(xfull + (i & 3) * 8, UNIT);
          if (i < NRS) tma2d(base + (i & 3) * GST_BYTES, &maps.x, kt * 64, rb * 128, xfull + (i & 3) * 8);
          else bulk_load_stream(base + (i & 3) * GST_BYTES, g_act + (uint32_t)(rb * 80 + kt) * UNIT, UNIT, xfull + (i & 3) * 8);
        }
      }
      prefetch_map(&maps.wo);
#pragma unroll 1
      for (int t = 0; t < 4; t++) {
        if (t & 1) mbar_wait(bar_od, t >> 1);
#pragma unroll 1
        for (int p = 0; p < 32768 / OPS; p++) {
          const uint32_t w = p / (16384 / OPS), c = (p / (8192 / OPS)) & 1, off = w * 8192 + (p % (8192 / OPS)) * OPS;
          mbar_wait(bar_ofull + (t & 1) * 16 + w * 8, t >> 1);
          if (elect_one()) {
            bulk_store(g_act + (uint32_t)(rb * 80 + 16 + (cj * 4 + t) * 2 + c) * UNIT + off, base + unit_of(QT, 2 * t + c) + off, OPS);
            asm volatile("cp.async.bulk.commit_group;" ::: "memory");
            asm volatile("cp.async.bulk.wait_group.read 0;" ::: "memory");
          }
        }
        if (elect_one()) {
          mbar_arrive(t < 3 ? bar_ofree + t * 8 : bar_res);
          asm volatile("cp.async.bulk.wait_group 0;" ::: "memory");
          fence_async();
          red_release(&g_cnt_o[((rb * 4 + t) * 2 + (cj >> 2)) * 32], 2);
        }
        if (t) {
          wait_counter(&g_cnt_o[(rb * 8 + 2 * t + (cj & 1)) * 32], target);
          if (t & 1) wait_counter(&g_cnt_o[(rb * 8 + (t == 1 ? cj & 1 : 7 - (cj & 1))) * 32], target);
          if (elect_one()) mbar_arrive(t == 1 ? bar_ofree + 24 : bar_cnt + t * 8 - 16);
        }
      }
      PROF(2, lane == 0, 27);
      const uint32_t tag = epoch % 3 + 1;
      const uint32_t* inbox = g_cand + (b >> 1) % CR * 512 + (lane & 15) * CS;
      mbar_wait(bar_ring + 16, 0);
      uint32_t c0 = ld_relaxed(inbox), n = 0;
#define CAND_STEP(cv)                                                                                        \
      {                                                                                                      \
        const bool valid = (cv & 3u) == tag, all = __all_sync(0xffffffffu, valid);                           \
        const uint32_t best = __reduce_max_sync(0xffffffffu, valid ? cv : 0u);                               \
        const uint32_t blk = __ffs(__ballot_sync(0xffffffffu, cv == best)) - 1;                              \
        if (best) sts2(par + PAR_CONST + 56, best, (blk << 7 | (~best >> 2 & 127)) | (all ? 0x1800 : 0x800)); \
        if (all) break;                                                                                      \
        cv = ld_relaxed(inbox);                                                                              \
      }
      while (true) { CAND_STEP(c0) watchdog(n); }
    } else {
      const int t2 = tid - 320;
      if (late && warp == 10) {
        mbar_wait(bar_hx, 0);
        if (elect_one()) {
          tma2d(stage, &maps.wm, (b >> 1) * 32, rank * 512, bar_hw);
          tma2d(stage + 16384, &maps.wm, (b >> 1) * 32, rank * 512 + 256, bar_hw);
        }
      }
      {
        const uint32_t tag = epoch % 3 + 1;
        mbar_wait(bar_hx + 8, 0);
        mbar_wait(bar_hw, 0);
        __nanosleep(late ? OSL2 : OSL);
        {
          const uint32_t t7 = (warp & 1) * 64 + (lane >> 4) * 32 + 16 + (lane & 15);
          const uint32_t* pm = g_modp + ((cj * 128 + t7 * 4) & (DM - 1));
          uint4 m0, m1, m2, m3;
          uint32_t n = 0;
          do {
            m0 = ld_relaxed4(pm); m1 = ld_relaxed4(pm + 2 * DM); m2 = ld_relaxed4(pm + DM); m3 = ld_relaxed4(pm + 3 * DM);
            watchdog(n);
          } while (!__all_sync(0xffffffffu, tag_ok(m0, tag) && tag_ok(m1, tag) && tag_ok(m2, tag) && tag_ok(m3, tag)));
          write_table(par, false, t7, m0, m1);
          write_table(par, true, t7, m2, m3);
          mbar_arrive(bar_mod2);
        }
      }
      mbar_wait(bar_hpub + (warp & 1) * 8, 0);
      PROF(1, t2 == 0, 24);
#pragma unroll 1
      for (int c = 0; c < 8; c++) {
        const uint32_t off = (warp & 1) * UNIT + c * 2048 + lane * 16;
        uint8_t* dst = g_act + (uint32_t)(rb * 80 + cj * 2) * UNIT + off;
        const uint4 v0 = lds4(stage + off), v1 = lds4(stage + off + 512), v2 = lds4(stage + off + 1024), v3 = lds4(stage + off + 1536);
        stg4(dst, v0); stg4(dst + 512, v1); stg4(dst + 1024, v2); stg4(dst + 1536, v3);
      }
      __syncwarp();
      PROF(1, t2 == 0, 15);
      if (lane == 0) {
        mbar_arrive(bar_pread);
        red_release(&g_cnt_h[rb * 32 + cj * 2 + (warp & 1)], 1);
        PROF(1, t2 == 0, 25);
        prefetch_map(&maps.wg); prefetch_map(&maps.wu); prefetch_map(&maps.wd); prefetch_map(&maps.out);
      }
      __syncwarp();
      if (b < NFFN) {
        mbar_wait(bar_go2, 0);
        const __nv_bfloat16* pg = ((b & 1) ? P.w_up : P.w_gate) + (b >> 1) * 64 + (size_t)t2 * FF;
        const __nv_bfloat16* pd = P.w_down + (size_t)b * 32768 + t2 * 64;
        PROF(2, t2 == 0, 13);
#pragma unroll 1
        for (int i = 0; i < WN; i += WB) {
          uint32_t v[WB];
#pragma unroll
          for (int u = 0; u < WB; u++) {
            const int k = i + u;
            asm volatile("ld.global.cg.L2::128B.u32 %0, [%1];" : "=r"(v[u]) : "l"(k < 16 ? pg + (size_t)k * 64 * FF : pd + (k - 16) * 4096));
          }
#pragma unroll
          for (int u = 1; u < WB; u++) v[0] ^= v[u];
          sts1(par + PAR_SINK + t2 * 4, v[0]);
        }
        PROF(2, t2 == 0, 14);
      }
      const uint32_t tag = epoch % 3 + 1;
      mbar_wait(bar_go, 0);
      bar_sync(4, 64);
      if (warp == 10) {
        const uint32_t* src = g_mod + 2 * DM + cj * 128 + lane * 4;
        const uint2 wr = *reinterpret_cast<const uint2*>(P.w_r + cj * 128 + lane * 4);
        uint4 vga, vsb, vcb, vgb;
        uint32_t n = 0;
        do {
          vga = ld_relaxed4(src); vsb = ld_relaxed4(src + DM); vcb = ld_relaxed4(src + 2 * DM); vgb = ld_relaxed4(src + 3 * DM);
          watchdog(n);
        } while (!__all_sync(0xffffffffu, tag_ok(vga, tag) && tag_ok(vsb, tag) && tag_ok(vcb, tag) && tag_ok(vgb, tag)));
        const float c0 = rbf(1.f + bf_hi(vcb.x)), c1 = rbf(1.f + bf_hi(vcb.y)), c2 = rbf(1.f + bf_hi(vcb.z)), c3 = rbf(1.f + bf_hi(vcb.w));
        const float a0 = c0 * bf_lo(wr.x), a1 = c1 * bf_hi(wr.x), a2 = c2 * bf_lo(wr.y), a3 = c3 * bf_hi(wr.y);
        const uint32_t h0 = pack_bf(a0, a1), h1 = pack_bf(a2, a3);
        const uint32_t t1 = par + PAR_T1 + (lane >> 2) * 64 + (lane & 1) * 32 + (lane & 2) * 2;
        sts1(t1, h0); sts1(t1 + 8, pack_bf(a0 - bf_lo(h0), a1 - bf_hi(h0)));
        sts1(t1 + 16, h1); sts1(t1 + 24, pack_bf(a2 - bf_lo(h1), a3 - bf_hi(h1)));
        const uint32_t tg = par + PAR_SINK + (lane >> 3) * 64 + (lane & 1) * 32 + (lane & 6) * 2;
        sts1(tg, __byte_perm(vga.x, vga.y, 0x7632)); sts1(tg + 16, __byte_perm(vga.z, vga.w, 0x7632));
        sts4(par + PAR_T2 + lane * 32, make_uint4(pack_bf(c0, c1), __byte_perm(vsb.x, vsb.y, 0x7632), __byte_perm(vgb.x, vgb.y, 0x7632), __byte_perm(vga.x, vga.y, 0x7632)));
        sts4(par + PAR_T2 + lane * 32 + 16, make_uint4(pack_bf(c2, c3), __byte_perm(vsb.z, vsb.w, 0x7632), __byte_perm(vgb.z, vgb.w, 0x7632), __byte_perm(vga.z, vga.w, 0x7632)));
      } else {
        const uint4 g = poll4((lane & 8) ? g_mod + 8 - (lane & 1) * 4 : g_mod + 5 * DM + (b >> 4) * 128 + (lane & 7) * 16 + (b & 12), tag);
        sts1(par + PAR_CONST + 60, 0);
        if (lane < 8) sts1(par + PAR_CONST + 16 + lane * 4, (b & 2) ? ((b & 1) ? g.w : g.z) : ((b & 1) ? g.y : g.x));
        else if (lane < 10) sts2(par + PAR_CONST + (lane - 8) * 8, __float_as_uint(untag_sum(g.x, g.y) + untag_sum(g.z, g.w)), epoch);
      }
      __syncwarp();
#pragma unroll 4
      for (int q = 0; q < 32; q++) st_b128(g_xch + ((size_t)b * 8 * 256 + q * 64 + t2) * 4, (epoch & 1) << 16, 0, 0, 0);
      for (int q = 0; q < 2; q++) st_relaxed4(g_stats + ((size_t)cj * SEQ + rb * 128 + q * 64 + t2) * 4, 0, 0, 0, 0);
      if (b < NFFN)
        for (int q = 0; q < 2; q++) st_relaxed4(ypart_slot(b, q * 64 + t2), 0, 0, 0, 0);
      st_relaxed4(g_row + rb * 2 * DM + (t2 >> 5) * DM + cj * 128 + (t2 & 31) * 4, 0, 0, 0, 0);
      __threadfence();
      mbar_arrive(bar_par);
      mbar_wait(bar_gate, 0);
      uint32_t have = 0, n = 0;
      while (true) {
        const uint32_t st = lds1(par + PAR_CONST + 60) >> 7;
        if ((st & 31) != have) {
          const uint32_t* hsrc = g_row + (st & 15) * 2 * DM + t2 * 4;
          uint4 hv[4];
          bool ok = true;
#pragma unroll
          for (int i = 0; i < 4; i++) hv[i] = ld_pairs(hsrc + i * 256);
#pragma unroll
          for (int i = 0; i < 4; i++) {
            sts2(base + ((FT_G >> i * 4) & 15) * UNIT + (warp & 1) * 8192 + 256 + lane * 8, hv[i].x, hv[i].z);
            ok = ok && hv[i].y == tag && hv[i].w == tag;
          }
          have = __all_sync(0xffffffffu, ok) ? st & 31 : 0;
        }
        if ((st ^ have) == 32) break;
        watchdog(n);
      }
      mbar_arrive(bar_sel);
    }
    __syncwarp();
    cluster_arrive();
    {
      const uint32_t tag = epoch % 3 + 1, t3 = tid - 256;
      mbar_wait(bar_win, 0);
      uint2 win = lds2(par + PAR_CONST + 56);
      win.y &= 0x7ff;
      const uint32_t* fsrc = g_row + (win.y >> 7) * 2 * DM + (b >> 4) * 128 + (t3 & 7) * 16 + (b & 6) * 2 + ((b >> 2) & 2);
      const uint32_t* ysrc = ypart_slot(min(t3, NFFN - 1), b);
      uint2 fh = ld_pair(fsrc), fx = ld_pair(fsrc + DM);
      uint4 ya = ld_b128(ysrc);
      const float rwin = __uint_as_float(((int)win.x < 0 ? win.x & 0x7fffffffu : ~win.x) & ~0x1ffu);
      const float rs = rbf(rcp(1.f + __expf(-rbf(rwin))));
      uint32_t n = 0;
      while (__any_sync(0xffffffffu, fh.y != tag || fx.y != tag)) { fh = ld_pair(fsrc); fx = ld_pair(fsrc + DM); watchdog(n); }
      while (true) {
        const bool miss = ((ya.x & 1) | (ya.y & 1) << 1) != tag;
        if (!__any_sync(0xffffffffu, miss)) break;
        if (miss) ya = ld_b128(ysrc);
        watchdog(n);
      }
      PROF(8, t3 == 0, 5);
      float y[8] = {bf_lo(ya.x & ~1u), bf_hi(ya.x), bf_lo(ya.y & ~1u), bf_hi(ya.y), bf_lo(ya.z), bf_hi(ya.z), bf_lo(ya.w), bf_hi(ya.w)};
#pragma unroll
      for (int h = 4; h > 0; h >>= 1) {
        const bool up = lane & (h * 2);
#pragma unroll
        for (int e = 0; e < h; e++) y[e] = (up ? y[e + h] : y[e]) + __shfl_xor_sync(0xffffffffu, up ? y[e] : y[e + h], h * 2);
      }
      y[0] += __shfl_xor_sync(0xffffffffu, y[0], 1);
      if (!(lane & 1)) sts1(par + PAR_RED + 64 + t3 * 2, __float_as_uint(y[0]));
      bar_sync(4, 128);
      if (t3 < 8) {
        float y0 = 0.f;
#pragma unroll
        for (int w7 = 0; w7 < 7; w7++) y0 += __uint_as_float(lds1(par + PAR_RED + 64 + w7 * 32 + t3 * 4));
        const uint32_t gv = lds1(par + PAR_CONST + 16 + t3 * 4);
        const uint32_t upd = hmul2(pack_bf(y0, y0), pack_bf(rs, rs));
        const uint32_t r = hadd2(fx.x, hmul2(__byte_perm(gv, gv, 0x3232), hadd2(fh.x, upd)));
        reinterpret_cast<uint16_t*>(P.out)[(size_t)win.y * DM + (b >> 4) * 128 + t3 * 16 + (b & 15)] = (b & 1) ? r >> 16 : r;
        if (b == 0 && t3 == 0) st_relaxed(&g_epoch, epoch + 1);
      }
      PROF(31, t3 == 0, 36);
    }
    cluster_wait();
  } else {
    const int wg = warp >> 2;

    uint32_t tag;
    {
      uint32_t* const pmod = g_modp + rank * 2 * DM + (b >> 1) * 32 + lane;
      uint32_t* const pln = g_ln1 + (rb * 128 + cj * 16 + warp) * 4;
      uint32_t sc[8];
#pragma unroll
      for (int k = 0; k < 8; k++) sc[k] = ldg_nc1(P.c + rank * 512 + warp * 64 + k * 8 + (lane & 3) * 2);
      const uint32_t epoch = ld_relaxed(&g_epoch);
      if (warp == 0) st_relaxed(pmod, 0);
      if (lane == 0) { st_b128(pln, 0, 0, 0, 0); st_b128(pln + 32, 0, 0, 0, 0); }
      asm volatile("setmaxnreg.inc.sync.aligned.u32 232;");
      bar_sync(1, 320);
#pragma unroll
      for (int k = 0; k < 8; k++) sc[k] = pack_bf(silu_f(bf_lo(sc[k])), silu_f(bf_hi(sc[k])));
      keep(sc);
      tag = epoch % 3 + 1;
#pragma unroll
      for (int part = 0; part < 4; part++) {
        if (!(part & 1)) {
          const uint32_t xa = base + (2 + part / 2) * GST_BYTES + warp * 2048 + lane * 16;
          mbar_wait(bar_hx + part * 4, 0);
          float s0 = 0.f, s1 = 0.f, q0 = 0.f, q1 = 0.f;
#pragma unroll
          for (int q = 0; q < 4; q++) {
            const uint4 xv = lds4(xa + q * 512);
            const uint32_t u[4] = {xv.x, xv.y, xv.z, xv.w};
#pragma unroll
            for (int e = 0; e < 4; e++) { const float lo = bf_lo(u[e]), hi = bf_hi(u[e]); s0 += lo; s1 += hi; q0 += lo * lo; q1 += hi * hi; }
          }
          s0 += s1; q0 += q1;
#pragma unroll
          for (int o = 16; o > 0; o >>= 1) { s0 += __shfl_xor_sync(0xffffffffu, s0, o); q0 += __shfl_xor_sync(0xffffffffu, q0, o); }
          const float mean = s0 * (1.f / DM);
          float mb, sd;
          ln_scalars(mean, fmaxf(q0 * (1.f / DM) - mean * mean, 0.f), mb, sd);
          uint32_t ih, il;
          split_inv(sd, ih, il);
          if (lane == 0) st_b128(pln + part * 16, pack_bf(mb, mb), ih, il, tag);
          PROF(1, tid == 0 && part == 2, 4);
        } else if (late == (part == 3)) {
          const uint32_t fr = (lane & 7) + (lane >> 4) * 8, tq = lane & 3;
          const uint32_t wa = stage + warp * 4096 + fr * 64 + ((((lane >> 3) & 1) ^ ((fr >> 1) & 3)) << 4);
          float d0[4] = {0.f, 0.f, 0.f, 0.f}, d1[4] = {0.f, 0.f, 0.f, 0.f};
          mbar_wait(bar_hw, 0);
#pragma unroll
          for (int ks = 0; ks < 4; ks++) {
            uint32_t w[8];
            ldmatrix4t(wa + ks * 1024, w[0], w[1], w[2], w[3]);
            ldmatrix4t((wa ^ 32) + ks * 1024, w[4], w[5], w[6], w[7]);
            mma16816(d0, w[0], w[1], w[2], w[3], sc[2 * ks], sc[2 * ks + 1]);
            mma16816(d1, w[4], w[5], w[6], w[7], sc[2 * ks], sc[2 * ks + 1]);
          }
          sts1(base + 2 * GST_BYTES + warp * 2048 + (tq * 8 + (lane >> 2)) * 4, __float_as_uint((tq & 2) ? ((tq & 1) ? d1[2] : d1[0]) : ((tq & 1) ? d0[2] : d0[0])));
          bar_sync(1, 256);
          if (warp == 0) {
            float s = 0.f;
#pragma unroll
            for (int w8 = 0; w8 < 8; w8++) s += __uint_as_float(lds1(base + 2 * GST_BYTES + w8 * 2048 + lane * 4));
            st_relaxed(pmod, (__float_as_uint(s) & ~3u) | tag);
          }
          PROF(1, tid == 0, 3);
        }
      }
      cluster_wait();
      if (wg == 1) bar_arrive(2, 256);
    }

    float f0 = 0.f, f1 = 0.f;
    const uint32_t rempty = lane < 2 ? mapa(bempty, lane & 1) : 0;
    constexpr uint32_t GE = NSLOT * 8 + 32;
    float o[64], s[64];
#pragma unroll 1
    for (int ps = 0; ps < 3; ps++) {
      {
        const uint32_t xt = ps == 1 ? XT1 : XT2, wt = ps == 1 ? WT1 : WT2;
        const int nst = ps == 2 ? 28 : 14;
        if (ps == 0) {
          float ga[64], gb[64];
#pragma unroll
          for (int i = 0; i < 64; i++) { ga[i] = 0.f; gb[i] = 0.f; }
          uint32_t a[2][16];
          const uint32_t l = fresh_lane();
          uint32_t fa[4];
#pragma unroll
          for (int kk = 0; kk < 4; kk++) fa[kk] = (base + wg * 8192 + frag_offset(warp)) ^ (kk * 32);
          const uint32_t mt = par + (l & 3) * 16;
          auto fetch = [&](int i, uint32_t (&f)[16], uint32_t z) {
            mbar_wait(xfull + (i & 3) * 8, i >> 2);
#pragma unroll
            for (int kk = 0; kk < 4; kk++) ldmatrix4(fa[kk] + (i & 3) * GST_BYTES + z, f[4 * kk], f[4 * kk + 1], f[4 * kk + 2], f[4 * kk + 3]);
          };
          const bool oddw = warp & 2;
          uint4 r0, r1;
          {
            const uint32_t t7 = (warp & 1) * 64 + (l >> 4) * 32 + (l & 15);
            const uint32_t* pm = g_modp + wg * DM + ((cj * 128 + t7 * 4) & (DM - 1));
            const uint32_t* pr = g_ln1 + (rb * 128 + warp * 16 + (l >> 2)) * 4;
            uint4 m0 = make_uint4(tag, tag, tag, tag), m1 = m0;
            if (!oddw) { m0 = ld_relaxed4(pm); m1 = ld_relaxed4(pm + 2 * DM); }
            r0 = ld_b128(pr); r1 = ld_b128(pr + 32);
            fetch(0, a[0], 0); fetch(1, a[1], 0);
            uint32_t n = 0;
            bool written = false;
#pragma unroll 1
            while (true) {
              uint32_t miss;
              asm volatile("{ .reg .pred p0, p1, p2, p3; .reg .b32 t, u;\n"
                           "lop3.b32 t, %1, %2, %19, 0x7e; lop3.b32 u, %3, %4, %19, 0x7e; or.b32 t, t, u; and.b32 t, t, 3; setp.ne.u32 p0, t, 0;\n"
                           "lop3.b32 t, %5, %6, %19, 0x7e; lop3.b32 u, %7, %8, %19, 0x7e; or.b32 t, t, u; and.b32 t, t, 3; setp.ne.u32 p1, t, 0;\n"
                           "setp.ne.u32 p2, %12, %19; setp.ne.u32 p3, %16, %19;\n"
                           "@p0 ld.relaxed.gpu.global.v4.u32 {%1, %2, %3, %4}, [%17];\n"
                           "@p1 ld.relaxed.gpu.global.v4.u32 {%5, %6, %7, %8}, [%17 + 8192];\n"
                           "@p2 ld.relaxed.gpu.global.v4.u32 {%9, %10, %11, %12}, [%18];\n"
                           "@p3 ld.relaxed.gpu.global.v4.u32 {%13, %14, %15, %16}, [%18 + 128];\n"
                           "or.pred p0, p0, p1; or.pred p2, p2, p3; vote.sync.any.pred p0, p0, 0xffffffff; vote.sync.any.pred p2, p2, 0xffffffff;\n"
                           "selp.u32 t, 1, 0, p0; selp.u32 u, 2, 0, p2; or.b32 %0, t, u; }"
                           : "=r"(miss), "+r"(m0.x), "+r"(m0.y), "+r"(m0.z), "+r"(m0.w), "+r"(m1.x), "+r"(m1.y), "+r"(m1.z), "+r"(m1.w),
                             "+r"(r0.x), "+r"(r0.y), "+r"(r0.z), "+r"(r0.w), "+r"(r1.x), "+r"(r1.y), "+r"(r1.z), "+r"(r1.w)
                           : "l"(pm), "l"(pr), "r"(tag) : "memory");
              if (!(miss & 1) && !written) {
                written = true;
                if (!oddw) write_table(par, wg, t7, m0, m1);
                mbar_arrive(bar_mod);
              }
              if (!miss) break;
              watchdog(n);
            }
          }
          const uint32_t zero = r0.w ^ tag;
          auto normalize = [&](uint32_t (&f)[16]) {
#pragma unroll
            for (int k = 0; k < 16; k += 2) { f[k] = ln_norm(f[k], r0.x, r0.y, r0.z); f[k + 1] = ln_norm(f[k + 1], r1.x, r1.y, r1.z); }
          };
          auto modulate = [&](int i, uint32_t (&f)[16]) {
#pragma unroll
            for (int kk = 0; kk < 4; kk++) {
              const uint4 m = lds4(mt + slice_of(i) * 256 + kk * 64);
              f[4 * kk] = hfma2(f[4 * kk], m.x, m.z); f[4 * kk + 1] = hfma2(f[4 * kk + 1], m.x, m.z);
              f[4 * kk + 2] = hfma2(f[4 * kk + 2], m.y, m.w); f[4 * kk + 3] = hfma2(f[4 * kk + 3], m.y, m.w);
            }
            keep(f);
            mbar_arrive_pred(xempty + (i & 3) * 8, l == 0);
          };
          auto publish = [&](int u, uint32_t (&f)[16]) {
#pragma unroll
            for (int kk = 0; kk < 4; kk++) stmatrix4(fa[kk] + OFF_STAGE + u * UNIT, f[4 * kk], f[4 * kk + 1], f[4 * kk + 2], f[4 * kk + 3]);
            __syncwarp();
            mbar_arrive_pred(bar_hpub + u * 8, l == 0);
          };
          auto multiply = [&](int i, uint32_t (&f)[16]) {
            mbar_wait(gfull + (i & 3) * 8, i >> 2);
            const uint64_t db = make_desc(base + (i & 3) * GST_BYTES + UNIT, 8192, 1024);
            wg_fence();
#pragma unroll
            for (int kk = 0; kk < 4; kk++) mma256_rs(ga, gb, f[4 * kk], f[4 * kk + 1], f[4 * kk + 2], f[4 * kk + 3], db + kk * 128);
            wg_commit();
          };
          auto next = [&](int i, uint32_t (&f)[16]) {
            wg_wait<1>();
            mbar_arrive_cl(rempty, GE + ((i + 2) & 3) * 8);
            uint32_t z = zero;
#pragma unroll
            for (int k = 0; k < 16; k += 2) asm volatile("lop3.b32 %0, %1, %2, %0, 0xA8;" : "+r"(z) : "r"(f[k]), "r"(f[k + 1]));
            fetch(i, f, z);
            normalize(f);
            if (i == 2) { keep(f); mbar_wait(bar_mod2, 0); }
            modulate(i, f); multiply(i, f);
          };
          normalize(a[0]); normalize(a[1]);
          keep(a[0]); keep(a[1]);
          mbar_wait(bar_mod, 0);
          PROF(1, tid == 0, 2);
          modulate(0, a[0]); multiply(0, a[0]); publish(0, a[0]);
          modulate(1, a[1]); multiply(1, a[1]);
#pragma unroll 1
          for (int i = 2; i < NRS; i += 2) {
            next(i, a[0]);
            if (i == 2) publish(1, a[0]);
            next(i + 1, a[1]);
          }
          wg_wait<1>();
          mbar_arrive_cl(rempty, GE + ((NRS + 2) & 3) * 8);
#pragma unroll 1
          for (int i = NRS; i < 14; i++) {
            mbar_wait(xfull + (i & 3) * 8, (i >> 2) & 1);
            mbar_wait(gfull + (i & 3) * 8, (i >> 2) & 1);
            const uint32_t xa = base + (i & 3) * GST_BYTES;
            const uint64_t da = make_desc(xa + wg * 8192, 16, 1024), db = make_desc(xa + UNIT, 8192, 1024);
            if (i == 13) bar_sync(2 + wg, 256);
            wg_fence();
#pragma unroll
            for (int kk = 0; kk < 4; kk++) mma256_ss(ga, gb, da + kk * 2, db + kk * 128, 1);
            wg_commit();
            if (i == 13) bar_arrive(3 - wg, 256);
            wg_wait<1>();
            uint32_t z = zero;
#pragma unroll
            for (int k = 0; k < 16; k += 2) asm volatile("lop3.b32 %0, %1, %2, %0, 0xA8;" : "+r"(z) : "r"(a[1][k]), "r"(a[1][k + 1]));
            mbar_arrive_cl(rempty, GE + ((i + 3) & 3) * 8 + z);
            mbar_arrive_pred(xempty + ((i + 3) & 3) * 8, l == 0 && i != NRS);
          }
          mbar_wait(xfull + 16, 1);
          wg_wait<0>();
          keep(ga); keep(gb);
#pragma unroll
          for (int i = 0; i < 64; i++) {
            asm volatile("mov.b32 %0, %1;" : "=f"(s[i]) : "f"(ga[i]));
            asm volatile("mov.b32 %0, %1;" : "=f"(o[i]) : "f"(gb[i]));
          }
        } else {
          float ga[64], gb[64];
#pragma unroll
          for (int i = 0; i < 64; i++) {
            asm volatile("mov.b32 %0, %1;" : "=f"(ga[i]) : "f"(s[i]));
            asm volatile("mov.b32 %0, %1;" : "=f"(gb[i]) : "f"(o[i]));
          }
#pragma unroll 1
          for (int i = 0; i < nst; i++) {
            mbar_wait(gfull + (i & 3) * 8, (i >> 2) & 1);
            const uint64_t da = make_desc(base + unit_of(xt, i & 3) + wg * 8192, 16, 1024), db = make_desc(base + unit_of(wt, i & 3), 8192, 1024);
            if (i == nst - 1) bar_sync(2 + wg, 256);
            wg_fence();
#pragma unroll
            for (int kk = 0; kk < 4; kk++) mma256_ss(ga, gb, da + kk * 2, db + kk * 128, kk ? 1 : i);
            wg_commit();
            if (i == nst - 1) bar_arrive(3 - wg, 256);
            wg_wait<1>();
            mbar_arrive_cl(rempty, GE + ((i + 3) & 3) * 8, i != 0);
            PROF(4, tid == 0 && (i & 3) == 0, 40 + (ps - 1) * 4 + i / 4);
          }
          wg_wait<0>();
          keep(ga); keep(gb);
#pragma unroll
          for (int i = 0; i < 64; i++) {
            asm volatile("mov.b32 %0, %1;" : "=f"(s[i]) : "f"(ga[i]));
            asm volatile("mov.b32 %0, %1;" : "=f"(o[i]) : "f"(gb[i]));
          }
        }
        mbar_arrive_cl(rempty, GE + (ps == 2 ? 24 : 8));
        if (ps == 2) break;
      }
      const uint32_t qw = base + wg * 8192, qt = QT >> (16 * ps), at = ps ? AT1 : AT0;
      {
        const uint32_t wt = ps ? WT1 : WT0;
        const uint64_t da0 = make_desc(qw + unit_of(qt, 2), 16, 1024), da1 = make_desc(qw + unit_of(qt, 3), 16, 1024);
        const uint64_t db0 = make_desc(base + unit_of(wt, 2), 8192, 1024), db1 = make_desc(base + unit_of(wt, 3), 8192, 1024);
        mbar_wait(gfull + 16, 1);
        bar_sync(2 + wg, 256);
        wg_fence();
#pragma unroll
        for (int kk = 0; kk < 4; kk++) mma_ss<1>(s, da0 + kk * 2, db0 + kk * 128, 1);
        wg_commit();
        mbar_wait(xfull + 24, 1);
        mbar_wait(gfull + 24, 1);
        wg_fence();
#pragma unroll
        for (int kk = 0; kk < 4; kk++) mma_ss<1>(s, da1 + kk * 2, db1 + kk * 128, 1);
        wg_commit();
        bar_arrive(3 - wg, 256);
        mbar_wait(ps == 0 ? bar_pread : bar_ofree + 8, 0);
        wg_wait<0>();
        keep(s);
        PROF(2, tid == 0, 8 + ps * 8);
        uint32_t q[32];
        pack_p(s, q);
#pragma unroll
        for (int i = 0; i < 4; i++) stmatrix4((qw + unit_of(qt, 0) + frag_offset(warp)) ^ (i << 5), q[4 * i], q[4 * i + 1], q[4 * i + 2], q[4 * i + 3]);
        keep(q);
        bar_sync(2 + wg, 256);
        wg_fence();
#pragma unroll
        for (int kk = 0; kk < 8; kk++) mma_ss<1>(o, (kk < 4 ? da0 : da1) + (kk & 3) * 2, (kk < 4 ? db0 : db1) + UNIT / 16 + (kk & 3) * 128, 1);
        wg_commit();
        mbar_wait(bfull, 0);
        wg_fence();
        const uint64_t dk = make_desc(base + unit_of(at, 0), 16, 1024);
#pragma unroll
        for (int kk = 0; kk < 8; kk++) mma_rs<0>(s, q[4 * kk], q[4 * kk + 1], q[4 * kk + 2], q[4 * kk + 3], dk + (kk >> 2) * 1024 + (kk & 3) * 2, kk != 0);
        wg_commit();
        bar_arrive(3 - wg, 256);
#pragma unroll
        for (int i = 4; i < 8; i++) stmatrix4((qw + unit_of(qt, 1) + frag_offset(warp)) ^ ((i & 3) << 5), q[4 * i], q[4 * i + 1], q[4 * i + 2], q[4 * i + 3]);
        wg_wait<1>();
        keep(o);
        mbar_arrive_cl(rempty, GE + 16);
        mbar_arrive_cl(rempty, GE + 24);
        store_chunk<0>(o, qw + unit_of(qt, 2) + frag_offset(warp));
        store_chunk<1>(o, qw + unit_of(qt, 3) + frag_offset(warp));
        wg_wait<0>();
        keep(s);
        mbar_arrive_cl(rempty, 0);
      }
      PROF(4, tid == 0 && ps == 1, 61);
      float l0 = 0.f, l1 = 0.f;
      auto step = [&](auto odd_c, const int j, uint32_t (&pw)[32], uint32_t (&pr)[32]) {
        constexpr bool ODD = decltype(odd_c)::value;
        const bool first = !ODD && (j & 2) == 0, last = ODD && j == 7;
        const uint32_t ph = (j >> 1) & 1;
        float i0, i1, a0, a1;
        const bool so = !ODD && j == 4;
        if (so) { i0 = inv_quad_sum(l0); i1 = inv_quad_sum(l1); l0 = 0.f; l1 = 0.f; }
        bool redo = !ODD && (j | ps) == 0;
        while (true) {
          if (redo) {
            float m0 = fmaxf(s[0], s[1]), m1 = fmaxf(s[2], s[3]);
#pragma unroll
            for (int i = 1; i < 16; i++) { m0 = fmaxf(m0, fmaxf(s[4 * i], s[4 * i + 1])); m1 = fmaxf(m1, fmaxf(s[4 * i + 2], s[4 * i + 3])); }
            m0 = fmaxf(m0, __shfl_xor_sync(0xffffffffu, m0, 1)); m1 = fmaxf(m1, __shfl_xor_sync(0xffffffffu, m1, 1));
            m0 = fmaxf(m0, __shfl_xor_sync(0xffffffffu, m0, 2)); m1 = fmaxf(m1, __shfl_xor_sync(0xffffffffu, m1, 2));
            m0 *= SCL2; m1 *= SCL2;
            if (!first) {
              m0 = fmaxf(m0, f0); m1 = fmaxf(m1, f1);
              const float c0 = ex2(f0 - m0), c1 = ex2(f1 - m1);
              l0 *= c0; l1 *= c1;
              wg_wait<0>();
              keep(o);
#pragma unroll
              for (int i = 0; i < 16; i++) { o[4 * i] *= c0; o[4 * i + 1] *= c0; o[4 * i + 2] *= c1; o[4 * i + 3] *= c1; }
            }
            f0 = m0; f1 = m1;
          }
          float b0 = 0.f, b1 = 0.f;
          a0 = 0.f; a1 = 0.f;
#pragma unroll
          for (int i = 0; i < 16; i++) {
            const float e0 = ex2(fmaf(s[4 * i], SCL2, -f0)), e1 = ex2(fmaf(s[4 * i + 1], SCL2, -f0));
            const float e2 = ex2(fmaf(s[4 * i + 2], SCL2, -f1)), e3 = ex2(fmaf(s[4 * i + 3], SCL2, -f1));
            a0 += e0; b0 += e1; a1 += e2; b1 += e3;
            pw[2 * i] = pack_bf(e0, e1); pw[2 * i + 1] = pack_bf(e2, e3);
            if (i == VREL) {
#pragma unroll
              for (int k = 0; k < 2 * VREL + 2; k++) asm volatile("" : "+r"(pw[k])::"memory");
              mbar_wait(bar_mod, 0);
              wg_wait<0>();
              mbar_arrive_cl(rempty, ODD ? 16 : 0, !redo && (ODD || j));
#pragma unroll
              for (int k = 4 * VREL + 4; k < 64; k++) asm volatile("" : "+f"(s[k])::"memory");
            }
          }
          a0 += b0; a1 += b1;
          if (redo) break;
          redo = __any_sync(0xffffffffu, !(a0 + a1 < 0x1p90f) || (!ODD && fminf(a0, a1) < (first ? 0x1p-90f : 0.f)));
          if (!redo) break;
        }
        l0 += a0; l1 += a1;
        keep(pw);
        keep(o);
        if (so) store_chunk<0>(o, i0, i1, qw + unit_of(qt, 0) + frag_offset(warp));
        keep(o);
        if (j == (ODD ? 5 : 0)) { fence_async_smem(); if (ODD) mbar_arrive(bar_ofull + wg * 8); }
        mbar_wait(bfull + (ODD ? 24 : 8), ph);
        bar_sync(2 + wg, 256);
        if (!last) {
          const uint32_t qn = qt >> (j >= 3 ? 8 : 0);
          wg_fence();
          issue_qk(s, qw + unit_of(qn, 0), qw + unit_of(qn, 1), base + unit_of(at, ODD ? 3 : 1));
          wg_commit();
          mbar_wait(bfull + (ODD ? 0 : 16), ODD ? ph ^ 1 : ph);
        }
        if (so) { store_chunk<1>(o, i0, i1, qw + unit_of(qt, 1) + frag_offset(warp)); keep(o); }
        wg_fence();
        issue_pv(o, pw, base + unit_of(at, ODD ? (last ? 3 : 0) : 2), !first);
        wg_commit();
        bar_arrive(3 - wg, 256);
        wg_wait<1>();
        keep(s);
        mbar_arrive_cl(rempty, ODD ? 24 : 8, !last);
        PROF(4, tid == 0 && ps == 1, 51 + j);
      };
      uint32_t pa[32], pb[32];
#pragma unroll 1
      for (int j = 0; j < 8; j += 2) {
        step(std::false_type{}, j, pa, pb);
        step(std::true_type{}, j + 1, pb, pa);
      }
      {
        const float i0 = inv_quad_sum(l0), i1 = inv_quad_sum(l1);
        wg_wait<0>();
        keep(o);
        mbar_arrive_cl(rempty, 24);
        store_chunk<0>(o, i0, i1, qw + unit_of(qt, 2) + frag_offset(warp));
        store_chunk<1>(o, i0, i1, qw + unit_of(qt, 3) + frag_offset(warp));
        fence_async_smem();
        mbar_arrive(bar_ofull + 16 + wg * 8);
      }
      PROF(2, tid == 0, 10 + ps * 8);
    }

    const int ln = fresh_lane(), g = ln >> 2, tq = ln & 3, ct = warp * 32 + ln;
    const bool lane0 = ln == 0;
    const int lrow0 = warp * 16 + g;
    const int grow0 = rb * 128 + lrow0;
    const uint32_t res = base + OFF_RES, trow = res + wg * 8192 + frag_offset(warp);
    uint32_t xr[32];
    uint4 sv[4], own;
    uint32_t* sp[4];
#pragma unroll
    for (int k = 0; k < 4; k++) sp[k] = g_stats + ((((tq >> 1) * 4 + k) ^ cj) * SEQ + grow0 + (tq & 1) * 8) * 4;
    {
      const uint64_t da = make_desc(base + wg * 8192, 16, 1024), db = make_desc(base, 8192, 1024);
      constexpr int U = UNIT / 16;
#define HALF_STAGE(acc, xu, wu) _Pragma("unroll") for (int kk = 0; kk < 4; kk++) mma_ss<1>(acc, da + (xu) * U + kk * 2, db + (wu) * U + kk * 128, 1)
      PROF(10, ct == PT, 19); STAMP(0);
      cluster_arrive();
      mbar_wait(gfull, 1);
      mbar_wait(gfull + 8, 1);
      bar_sync(2 + wg, 256);
      wg_fence();
      HALF_STAGE(o, 7, 1);
      HALF_STAGE(o, 8, 3);
      wg_commit();
      STAMP(16);
      mbar_wait(gfull + 16, 1);
      STAMP(17);
      wg_fence();
      HALF_STAGE(o, 6, 11);
      wg_commit();
      bar_arrive(3 - wg, 256);
      mbar_wait(bar_par, 0);
      uint32_t* xo = g_xch + ((size_t)b * 8 * 256 + ct) * 4;
      const uint32_t* xi = g_xch + ((size_t)(b ^ 2) * 8 * 256 + ct) * 4;
      const uint32_t par1 = (~lds1(par + PAR_CONST + 4) & 1) << 16;
      wg_wait<1>();
      mbar_arrive_pred(bar_rel, lane0);
      wg_wait<0>();
      keep(o);
      mbar_arrive_pred(bar_ring, lane0);
      PROF(8, ct == PT, 20); STAMP(1);
#define SEND(i) st_b128(xo + (i) * 1024, (pack_bf(o[8 * (i)], o[8 * (i) + 1]) & ~0x10000u) | par1, pack_bf(o[8 * (i) + 2], o[8 * (i) + 3]), \
                        pack_bf(o[8 * (i) + 4], o[8 * (i) + 5]), pack_bf(o[8 * (i) + 6], o[8 * (i) + 7]))
#pragma unroll
      for (int i = 0; i < NS1; i++) SEND(i);
      PROF(8, ct == PT, 21); STAMP(2);
      bar_sync(2 + wg, 256);
      wg_fence();
      HALF_STAGE(s, 7, 0);
      HALF_STAGE(s, 8, 2);
      HALF_STAGE(s, 6, 10);
      wg_commit();
      bar_arrive(3 - wg, 256);
      STAMP(18);
      mbar_wait(gfull + 24, 1);
#pragma unroll
      for (int i = NS1; i < 8; i++) SEND(i);
      uint4 v[8];
      STAMP(19);
      mbar_wait(bar_xres, 0);
      wg_wait<0>();
      mbar_arrive_pred(bar_ring + 8, lane0);
      bar_sync(2 + wg, 256);
      STAMP(20);
#pragma unroll
      for (int i = 0; i < LD2; i++) v[i] = ld_b128(xi + i * 1024);
      mbar_wait(bar_xres, 0);
      wg_fence();
      HALF_STAGE(s, 9, 4);
      wg_commit();
      mbar_wait(bar_rx, 0);
      wg_fence();
      HALF_STAGE(s, 1, 5);
      wg_commit();
      bar_arrive(3 - wg, 256);
      STAMP(21);
#pragma unroll
      for (int i = LD2; i < 8; i++) v[i] = ld_b128(xi + i * 1024);
      mbar_wait(bar_xres, 0);
      wg_wait<0>();
      keep(s);
      mbar_arrive_pred(bar_ring + 16, lane0);
      PROF(10, ct == PT, 23); STAMP(4);
#pragma unroll
      for (int i = 0; i < 16; i += 2) ldmatrix4((trow ^ ((i & 7) << 4)) + (i >> 3) * 16384, xr[2 * i], xr[2 * i + 1], xr[2 * i + 2], xr[2 * i + 3]);
      uint32_t ga[16];
      uint4 bw[8];
#pragma unroll
      for (int i = 0; i < 8; i++) {
        if (!(i & 1)) {
          const uint4 t = lds4(par + PAR_SINK + i * 32 + tq * 16);
          ga[2 * i] = t.x; ga[2 * i + 1] = t.y; ga[2 * i + 2] = t.z; ga[2 * i + 3] = t.w;
        }
        bw[i] = lds4(par + PAR_T1 + i * 64 + tq * 16);
        if (!(g & 1)) { bw[i].x = 0x3f803f80u; bw[i].y = 0x3f803f80u; }
      }
      uint32_t pk[32];
      pack_p(s, pk);
      keep(pk);
      {
        uint32_t n = 0, miss;
        do {
          miss = 0;
#pragma unroll
          for (int i = 0; i < 8; i++) miss |= v[i].x ^ par1;
          miss = __any_sync(0xffffffffu, miss & 0x10000u);
          if (miss) {
#pragma unroll
            for (int i = 0; i < 8; i++)
              asm volatile("{ .reg .pred p; .reg .b32 t; xor.b32 t, %0, %5; and.b32 t, t, 0x10000; setp.ne.u32 p, t, 0;\n"
                           "@p ld.relaxed.gpu.global.v4.u32 {%0, %1, %2, %3}, [%4]; }"
                           : "+r"(v[i].x), "+r"(v[i].y), "+r"(v[i].z), "+r"(v[i].w) : "l"(xi + i * 1024), "r"(par1) : "memory");
          }
          watchdog(n);
        } while (miss);
      }
      PROF(8, ct == PT, 22); STAMP(3);
      float ds[4] = {0.f, 0.f, 0.f, 0.f}, dl[4] = {0.f, 0.f, 0.f, 0.f}, q0[4] = {0.f, 0.f, 0.f, 0.f}, q1[4] = {0.f, 0.f, 0.f, 0.f};
#pragma unroll
      for (int i = 0; i < 8; i++) {
        const uint32_t u0 = hfma2(ga[2 * i], hadd2(pk[4 * i], v[i].x & ~0x10000u), xr[4 * i]);
        const uint32_t u1 = hfma2(ga[2 * i], hadd2(pk[4 * i + 1], v[i].y), xr[4 * i + 1]);
        const uint32_t u2 = hfma2(ga[2 * i + 1], hadd2(pk[4 * i + 2], v[i].z), xr[4 * i + 2]);
        const uint32_t u3 = hfma2(ga[2 * i + 1], hadd2(pk[4 * i + 3], v[i].w), xr[4 * i + 3]);
        xr[4 * i] = u0; xr[4 * i + 1] = u1; xr[4 * i + 2] = u2; xr[4 * i + 3] = u3;
        mma16816(ds, u0, u1, u2, u3, bw[i].x, bw[i].y);
        mma16816(dl, u0, u1, u2, u3, bw[i].z, bw[i].w);
        mma16816(q0, u0, u1, u2, u3, u0, u2);
        mma16816(q1, u0, u1, u2, u3, u1, u3);
      }
      const float sqa = __shfl_sync(0xffffffffu, (g & 1) ? q0[1] : q0[0], g * 4 + (g >> 1));
      const float sqb = __shfl_sync(0xffffffffu, (g & 1) ? q1[3] : q1[2], g * 4 + (g >> 1));
      own = (tq & 1) ? make_uint4(__float_as_uint(ds[2]), __float_as_uint(sqb), __float_as_uint(ds[3] + dl[3]), tag)
                                 : make_uint4(__float_as_uint(ds[0]), __float_as_uint(sqa), __float_as_uint(ds[1] + dl[1]), tag);
      if (tq < 2) st_b128(sp[0], own.x, own.y, own.z, own.w);
#pragma unroll
      for (int k = 0; k < 4; k++) sv[k] = make_uint4(0, 0, 0, 0);
    }
    PROF(8, ct == PT, 29); STAMP(5);
    uint32_t mm, ih, il;
    float rbest;
    uint32_t wf[128];
    const uint32_t frow = (ln & 7) + (ln >> 4) * 8;
    const uint32_t wfo = base + (warp & 1) * 8192 + frow * 64 + ((((ln >> 3) & 1) ^ ((frow >> 1) & 3)) << 4);
#define LOAD_WF(m) _Pragma("unroll") for (int f = 0; f < 16; f++) {                                                   \
      const int r = ((f >> 1) * 4 + (m) * 2 + (f & 1)) * 4;                                                           \
      ldmatrix4t(((wfo + unit_of((m) ? FT_U : FT_G, warp >> 1)) ^ ((f & 1) * 32)) + (f >> 1) * 1024, wf[r], wf[r + 1], wf[r + 2], wf[r + 3]); \
    }
    bool early;
    {
#pragma unroll
      for (int i = 0; i < 16; i += 2) stmatrix4((trow ^ ((i & 7) << 4)) + (i >> 3) * 16384, xr[2 * i], xr[2 * i + 1], xr[2 * i + 2], xr[2 * i + 3]);
      const uint4 cst = lds4(par + PAR_CONST);
      const float A1 = __uint_as_float(cst.x), A2 = __uint_as_float(cst.z);
      uint32_t n = 0;
      early = false;
#pragma unroll 1
      while (true) {
        uint32_t miss;
        asm volatile("{ .reg .pred p0, p1, p2, p3; .reg .b64 u, v; .reg .b128 w;\n"
                     "setp.ge.u32 p0, %22, 2; setp.ne.and.u32 p0, %4, %21, p0; setp.ne.u32 p1, %8, %21; setp.ne.u32 p2, %12, %21; setp.ne.u32 p3, %16, %21;\n"
                     "@p0 ld.relaxed.gpu.global.v4.u32 {%1, %2, %3, %4}, [%17];\n"
                     "@p1 ld.relaxed.gpu.global.v4.u32 {%5, %6, %7, %8}, [%18];\n"
                     "@p2 ld.relaxed.gpu.global.v4.u32 {%9, %10, %11, %12}, [%19];\n"
                     "@p3 ld.relaxed.gpu.global.v4.u32 {%13, %14, %15, %16}, [%20];\n"
                     "or.pred p0, p0, p1; or.pred p2, p2, p3; or.pred p0, p0, p2; vote.sync.any.pred p0, p0, 0xffffffff; selp.u32 %0, 1, 0, p0; }"
                     : "=r"(miss), "+r"(sv[0].x), "+r"(sv[0].y), "+r"(sv[0].z), "+r"(sv[0].w), "+r"(sv[1].x), "+r"(sv[1].y), "+r"(sv[1].z), "+r"(sv[1].w),
                       "+r"(sv[2].x), "+r"(sv[2].y), "+r"(sv[2].z), "+r"(sv[2].w), "+r"(sv[3].x), "+r"(sv[3].y), "+r"(sv[3].z), "+r"(sv[3].w)
                     : "l"(sp[0]), "l"(sp[1]), "l"(sp[2]), "l"(sp[3]), "r"(tag), "r"(tq) : "memory");
        if (!miss) break;
        if (!early && (b >= NFFN || __all_sync(0xffffffffu, mbar_test(bar_box + (warp >> 1) * 8, 0)))) {
          early = true;
          LOAD_WF(0);
          __syncwarp();
          mbar_arrive_pred(bar_gate, lane0);
        }
        watchdog(n);
      }
      const uint4 v0 = tq < 2 ? own : sv[0], v1 = sv[1], v2 = sv[2], v3 = sv[3];
      PROF(8, ct == PT, 30); STAMP(6);
      float su = (__uint_as_float(v0.x) + __uint_as_float(v1.x)) + (__uint_as_float(v2.x) + __uint_as_float(v3.x));
      float sq = (__uint_as_float(v0.y) + __uint_as_float(v1.y)) + (__uint_as_float(v2.y) + __uint_as_float(v3.y));
      float dt = (__uint_as_float(v0.z) + __uint_as_float(v1.z)) + (__uint_as_float(v2.z) + __uint_as_float(v3.z));
      su += __shfl_xor_sync(0xffffffffu, su, 2); sq += __shfl_xor_sync(0xffffffffu, sq, 2); dt += __shfl_xor_sync(0xffffffffu, dt, 2);
      const float m = su * (1.f / DM);
      float mb, sd;
      ln_scalars(m, fmaxf(sq * (1.f / DM) - m * m, 0.f), mb, sd);
      const float inv = rcp(sd);
      rbest = (dt - mb * A1) * inv + A2;
      mm = pack_bf(mb, mb);
      ih = pack_bf(inv, inv);
      const float lo = inv - bf_lo(ih);
      il = pack_bf(lo, lo);
    }
    int ibest;
    {
      const uint32_t bits = __float_as_uint(rbest);
      const uint32_t key = (((int)bits < 0 ? ~bits : bits | 0x80000000u) & ~0x1ffu) | ((127 - lrow0 - (tq & 1) * 8) << 2) | tag;
      sts1(par + PAR_RED + warp * 4, __reduce_max_sync(0xffffffffu, key));
      PROF(8, ct == PT, 38); STAMP(7);
      bar_sync(1, 256);
      const uint4 ka = lds4(par + PAR_RED), kb = lds4(par + PAR_RED + 16);
      const uint32_t k2 = max(max(max(ka.x, ka.y), max(ka.z, ka.w)), max(max(kb.x, kb.y), max(kb.z, kb.w)));
      if (ct < CR && cj == 0) st_relaxed(g_cand + ct * 512 + rb * CS, k2);
      ibest = 127 - ((k2 >> 2) & 127);
    }
    PROF(8, ct == PT, 39); STAMP(8);
    if ((ibest >> 4) == warp) {
      const int src = (ibest & 7) * 4 + ((ibest >> 3) & 1), ch = g * 2;
      const uint32_t cm = __shfl_sync(0xffffffffu, mm, src), ch_ = __shfl_sync(0xffffffffu, ih, src), cl = __shfl_sync(0xffffffffu, il, src);
      const uint32_t xa = res + (ch >> 3) * 16384 + ibest * 128 + (((ch & 7) ^ (ibest & 7)) << 4) + tq * 4;
      const uint32_t x0 = lds1(xa), x1 = lds1(xa ^ 16);
      const uint2 p0 = lds2(par + PAR_T2 + ch * 64 + tq * 16), p1 = lds2(par + PAR_T2 + ch * 64 + 64 + tq * 16);
      uint32_t* dst = g_row + rb * 2 * DM + cj * 128 + ln * 4;
      st_pairs(dst, ln_mod(x0, cm, ch_, cl, p0.x, p0.y), ln_mod(x1, cm, ch_, cl, p1.x, p1.y), tag);
      st_pairs(dst + DM, x0, x1, tag);
      __syncwarp();
    }
    PROF(8, ct == PT, 37); STAMP(9);
    uint32_t wd[64];
    const uint32_t wda = base + unit_of(FT_D, warp >> 1) + (warp & 1) * 8192 + frow * 128 + ((((ln >> 3) & 1) ^ (ln & 7)) << 4);
#define LOAD_WD(f) ldmatrix4t((wda ^ ((((f) >> 1) & 3) * 32)) + ((f) >> 3) * 4096 + ((f) & 1) * 2048, wd[4 * (f)], wd[4 * (f) + 1], wd[4 * (f) + 2], wd[4 * (f) + 3])
    if (!early) {
      if (b < NFFN) mbar_wait(bar_box + (warp >> 1) * 8, 0);
      LOAD_WF(0);
      __syncwarp();
      mbar_arrive_pred(bar_gate, lane0);
    }
    if (b < NFFN) {
      const uint32_t own = base + unit_of(FT_G, warp >> 1) + (warp & 1) * 8192;
      mbar_wait(bar_box + (4 + (warp >> 1)) * 8, 0);
      LOAD_WF(1);
      uint32_t* const ydst = ypart_slot(b, warp * 16 + (tq & 1) * 8 + g);
      PROF(8, ct == PT, 31); STAMP(10);
      bool wdok;
      {
        uint32_t n = 0;
        while (!(wdok = __all_sync(0xffffffffu, mbar_test(bar_box + (8 + (warp >> 1)) * 8, 0))) && !__all_sync(0xffffffffu, mbar_test(bar_sel, 0))) watchdog(n);
      }
      if (wdok) {
#pragma unroll
        for (int f = 0; f < 16; f++) LOAD_WD(f);
      }
      STAMP(11);
      mbar_wait(bar_sel, 0);
      PROF(8, ct == PT, 33); STAMP(12);
      float d[8][4];
#pragma unroll
      for (int i = 0; i < 4; i++) { d[i][0] = 0.f; d[i][1] = 0.f; d[i][2] = 0.f; d[i][3] = 0.f; }
#pragma unroll
      for (int ks = 0; ks < 8; ks++) {
        const uint2 hb = lds2(own + 256 + ks * 32 + tq * 8);
#pragma unroll
        for (int mt = 0; mt < 4; mt++) {
          const int r = ks * 16 + mt * 4;
          mma16816(d[mt], wf[r], wf[r + 1], wf[r + 2], wf[r + 3], hb.x, hb.y);
        }
      }
      sts2(own + (tq * 8 + g) * 8, __float_as_uint((tq & 2) ? ((tq & 1) ? d[1][2] : d[1][0]) : ((tq & 1) ? d[0][2] : d[0][0])),
           __float_as_uint((tq & 2) ? ((tq & 1) ? d[3][2] : d[3][0]) : ((tq & 1) ? d[2][2] : d[2][0])));
      bar_sync(1, 256);
      uint32_t ab[4];
      {
        float G = 0.f, U = 0.f;
        uint2 pv[8];
#pragma unroll
        for (int w8 = 0; w8 < 8; w8++) pv[w8] = lds2(base + ln * 8 + ((FT_G >> (w8 >> 1) * 4) & 15) * UNIT + (w8 & 1) * 8192);
#pragma unroll
        for (int w8 = 0; w8 < 8; w8 += 2) {
          G += __uint_as_float(pv[w8].x) + __uint_as_float(pv[w8 + 1].x);
          U += __uint_as_float(pv[w8].y) + __uint_as_float(pv[w8 + 1].y);
        }
        const float act = rbf(silu_f(rbf(G))) * rbf(U);
        const uint32_t pk = pack_bf(act, __shfl_down_sync(0xffffffffu, act, 1));
#pragma unroll
        for (int i = 0; i < 4; i++) ab[i] = __shfl_sync(0xffffffffu, pk, i * 8 + tq * 2);
      }
      if (!wdok) {
        mbar_wait(bar_box + (8 + (warp >> 1)) * 8, 0);
#pragma unroll
        for (int f = 0; f < 16; f++) LOAD_WD(f);
      }
      PROF(8, ct == PT, 34); STAMP(13);
#pragma unroll
      for (int mt = 0; mt < 8; mt++) {
        d[mt][0] = 0.f; d[mt][1] = 0.f; d[mt][2] = 0.f; d[mt][3] = 0.f;
        mma16816(d[mt], wd[mt * 8], wd[mt * 8 + 1], wd[mt * 8 + 2], wd[mt * 8 + 3], ab[0], ab[1]);
        mma16816(d[mt], wd[mt * 8 + 4], wd[mt * 8 + 5], wd[mt * 8 + 6], wd[mt * 8 + 7], ab[2], ab[3]);
      }
      uint32_t yw[4];
#pragma unroll
      for (int i = 0; i < 4; i++) yw[i] = (tq & 1) ? pack_bf(d[2 * i][2], d[2 * i + 1][2]) : pack_bf(d[2 * i][0], d[2 * i + 1][0]);
      if (tq < 2) st_b128(ydst, (yw[0] & ~1u) | (tag & 1), (yw[1] & ~1u) | (tag >> 1), yw[2], yw[3]);
      PROF(8, ct == PT, 35); STAMP(14);
    }
    mbar_wait(bar_sel, 0);
    mbar_arrive_pred(bar_win, ct == 0);
    const int iwin = lds1(par + PAR_CONST + 60) & 0x7ff;
    const bool cand = (iwin >> 4) == rb * 8 + warp;
    {
      const uint32_t mm0 = __shfl_sync(0xffffffffu, mm, ln & ~1), mm1 = __shfl_sync(0xffffffffu, mm, ln | 1);
      const uint32_t ih0 = __shfl_sync(0xffffffffu, ih, ln & ~1), ih1 = __shfl_sync(0xffffffffu, ih, ln | 1);
      const uint32_t il0 = __shfl_sync(0xffffffffu, il, ln & ~1), il1 = __shfl_sync(0xffffffffu, il, ln | 1);
#pragma unroll 1
      for (int hf = 0; hf < 2; hf++) {
        uint32_t x[16];
#pragma unroll
        for (int i = 0; i < 8; i += 2) ldmatrix4((trow ^ (i << 4)) + hf * 16384, x[2 * i], x[2 * i + 1], x[2 * i + 2], x[2 * i + 3]);
#pragma unroll
        for (int i = 0; i < 8; i++) {
          const uint4 pv = lds4(par + PAR_T2 + (hf * 8 + i) * 64 + tq * 16);
          x[2 * i] = hfma2(hfma2(ln_norm(x[2 * i], mm0, ih0, il0), pv.x, pv.y), pv.z, x[2 * i]);
          x[2 * i + 1] = hfma2(hfma2(ln_norm(x[2 * i + 1], mm1, ih1, il1), pv.x, pv.y), pv.z, x[2 * i + 1]);
        }
#pragma unroll
        for (int i = 0; i < 8; i += 2) stmatrix4((trow ^ (i << 4)) + hf * 16384, x[2 * i], x[2 * i + 1], x[2 * i + 2], x[2 * i + 3]);
        if (!cand) fence_async_smem();
        __syncwarp();
        if (!cand && elect_one()) {
          tma2d_store(&maps.out, res + hf * 16384 + warp * 2048, cj * 128 + hf * 64, rb * 128 + warp * 16);
          asm volatile("cp.async.bulk.commit_group;" ::: "memory");
        }
      }
    }
    if (cand) {
      const int wrow0 = warp * 16;
#pragma unroll 2
      for (int p = 0; p < 8; p++) {
        const int row = 2 * p + (ln >> 4), ch = ln & 15;
        const uint4 v = lds4(res + (ch >> 3) * 16384 + (wrow0 + row) * 128 + (((ch & 7) ^ (row & 7)) << 4));
        if (rb * 128 + wrow0 + row != iwin) *reinterpret_cast<uint4*>(P.out + (size_t)(rb * 128 + wrow0 + row) * DM + cj * 128 + ch * 8) = v;
      }
    }
    asm volatile("cp.async.bulk.wait_group.read 0;" ::: "memory");
    PROF(8, ct == PT, 11); STAMP(15);
    cluster_wait();
  }
}

typedef CUresult (*EncodeFn)(CUtensorMap*, CUtensorMapDataType, cuuint32_t, void*, const cuuint64_t*, const cuuint64_t*,
                             const cuuint32_t*, const cuuint32_t*, CUtensorMapInterleave, CUtensorMapSwizzle,
                             CUtensorMapL2promotion, CUtensorMapFloatOOBfill);

void map2d(EncodeFn enc, CUtensorMap* m, const void* p, uint64_t rows, uint64_t cols, uint32_t brows) {
  cuuint64_t dims[2] = {cols, rows}, strides[1] = {cols * 2};
  cuuint32_t box[2] = {64, brows}, es[2] = {1, 1};
  enc(m, CU_TENSOR_MAP_DATA_TYPE_BFLOAT16, 2, const_cast<void*>(p), dims, strides, box, es, CU_TENSOR_MAP_INTERLEAVE_NONE,
      CU_TENSOR_MAP_SWIZZLE_128B, CU_TENSOR_MAP_L2_PROMOTION_L2_256B, CU_TENSOR_MAP_FLOAT_OOB_FILL_NONE);
}
void map2d_narrow(EncodeFn enc, CUtensorMap* m, const void* p, uint64_t rows, uint64_t cols, uint32_t brows) {
  cuuint64_t dims[2] = {cols, rows}, strides[1] = {cols * 2};
  cuuint32_t box[2] = {32, brows}, es[2] = {1, 1};
  enc(m, CU_TENSOR_MAP_DATA_TYPE_BFLOAT16, 2, const_cast<void*>(p), dims, strides, box, es, CU_TENSOR_MAP_INTERLEAVE_NONE,
      CU_TENSOR_MAP_SWIZZLE_64B, CU_TENSOR_MAP_L2_PROMOTION_L2_64B, CU_TENSOR_MAP_FLOAT_OOB_FILL_NONE);
}
void map3d(EncodeFn enc, CUtensorMap* m, const void* p, uint64_t rows, uint64_t cols, uint32_t brows, uint32_t nch) {
  cuuint64_t dims[3] = {64, rows, cols / 64}, strides[2] = {cols * 2, 128};
  cuuint32_t box[3] = {64, brows, nch}, es[3] = {1, 1, 1};
  enc(m, CU_TENSOR_MAP_DATA_TYPE_BFLOAT16, 3, const_cast<void*>(p), dims, strides, box, es, CU_TENSOR_MAP_INTERLEAVE_NONE,
      CU_TENSOR_MAP_SWIZZLE_128B, CU_TENSOR_MAP_L2_PROMOTION_L2_256B, CU_TENSOR_MAP_FLOAT_OOB_FILL_NONE);
}

}

extern "C" void kernel_launch(void* const* d_in, const int* in_sizes, int n_in, void* d_out, int out_size) {
  (void)in_sizes; (void)n_in; (void)out_size;
  static EncodeFn enc = nullptr;
  if (!enc) {
    void* fn = nullptr;
    cudaDriverEntryPointQueryResult st;
    cudaGetDriverEntryPoint("cuTensorMapEncodeTiled", &fn, cudaEnableDefault, &st);
    enc = (EncodeFn)fn;
    cudaFuncSetAttribute(fused_kernel, cudaFuncAttributeMaxDynamicSharedMemorySize, SMEM_BYTES);
  }
  Maps maps;
  map2d(enc, &maps.x, d_in[0], SEQ, DM, 128);
  map2d(enc, &maps.out, d_out, SEQ, DM, 16);
  map3d(enc, &maps.wq, d_in[3], DM, NQ, 64, 2);
  map3d(enc, &maps.k, d_in[1], 4 * SK, 128, 128, 1);
  map3d(enc, &maps.v, d_in[2], 4 * SK, 128, 128, 1);
  map3d(enc, &maps.wo, d_in[4], NQ, DM, 64, 2);
  map2d_narrow(enc, &maps.wg, d_in[7], DM, FF, 256);
  map2d_narrow(enc, &maps.wu, d_in[8], DM, FF, 256);
  map3d(enc, &maps.wd, d_in[9], FF, DM, 32, 4);
  map2d_narrow(enc, &maps.wm, d_in[11], DM, NMOD, 256);
  Ptrs p;
  p.x = (const __nv_bfloat16*)d_in[0];
  p.w_r = (const __nv_bfloat16*)d_in[6];
  p.w_gate = (const __nv_bfloat16*)d_in[7];
  p.w_up = (const __nv_bfloat16*)d_in[8];
  p.w_down = (const __nv_bfloat16*)d_in[9];
  p.c = (const __nv_bfloat16*)d_in[10];
  p.w_mod = (const __nv_bfloat16*)d_in[11];
  p.out = (__nv_bfloat16*)d_out;
  fused_kernel<<<NMAIN + NHELP, 384, SMEM_BYTES>>>(maps, p);
}
```

```cpp
#include <cuda_runtime.h>
#include <cuda_bf16.h>
#include <cuda.h>
#include <stdint.h>
#include <type_traits>

#define HD 2
#define HDX 2
#define NRS 8
#define OSL 900
#define OSL2 400
#define RSL 40
#define VREL 5
#define OPS 8192
#define ODS1 5
#define ODS 7
#define PG0 15
#define WB 2
#define WN 20
#define HU 32
#define RES0 17
#define RES1 20
#define GOST 20
#define NS1 5
#define LD2 4
#define FPACE0 2
#define FPACE 3
#define CR 8
#define CS 8

namespace {

constexpr int SEQ = 2048, DM = 1024, NQ = 4096, SK = 2048, WIN = 512, FF = 3584, NMOD = 6144;
constexpr int NMAIN = 128, NHELP = 4, NFFN = 112;
constexpr int NSLOT = 4, SLOT_BYTES = 32768, UNIT = 16384, GST_BYTES = 3 * UNIT;
constexpr uint32_t XT1 = 0xDCBA, XT2 = 0x9687;
constexpr uint32_t WT0 = 0xA741, WT1 = 0x7420, WT2 = 0x4A20;
constexpr uint32_t AT0 = WT1, AT1 = WT2;
constexpr uint32_t QT = 0xDC9696DC;
constexpr int OFF_STAGE = 12 * UNIT;
constexpr uint32_t FT_G = 0x07B3, FT_U = 0xA628, FT_D = 0x5149;
constexpr int OFF_RES = 12 * UNIT;
constexpr int OFF_PAR = 14 * UNIT;
constexpr int OFF_BAR = OFF_PAR + 2528;
constexpr int SMEM_BYTES = OFF_BAR + 544;
static_assert(SMEM_BYTES <= 232448, "smem");

constexpr int PAR_T1 = 0;
constexpr int PAR_T2 = 512;
constexpr int PAR_CONST = 1536;
constexpr int PAR_RED = 1600;
constexpr int PAR_SINK = 2176;

struct Maps {
  CUtensorMap x, wq, k, v, wo, wg, wu, wd, wm, out;
};
struct Ptrs {
  const __nv_bfloat16 *x, *w_r, *c, *w_mod, *w_gate, *w_up, *w_down;
  __nv_bfloat16* out;
};

__device__ __align__(1024) uint8_t g_act[16 * 80 * UNIT];
__device__ __align__(128) uint32_t g_mod[NMOD];
__device__ __align__(128) uint32_t g_modp[2 * 2 * DM];
__device__ __align__(128) uint32_t g_ln1[SEQ * 4];
__device__ __align__(128) uint32_t g_cnt_h[16 * 32];
__device__ __align__(128) uint32_t g_cnt_o[128 * 32];
__device__ __align__(128) uint32_t g_xch[NMAIN * 8 * 256 * 4];
__device__ __align__(128) uint32_t g_stats[8 * SEQ * 4];
__device__ __align__(128) uint32_t g_cand[CR * 512];
__device__ __align__(128) uint32_t g_row[16 * 2 * DM];
__device__ __align__(128) uint32_t g_ypart[NMAIN * NFFN * 4];
__device__ __forceinline__ uint32_t* ypart_slot(int writer, int reader) { return g_ypart + (writer * NMAIN + reader) * 4; }
__device__ uint32_t g_epoch;

__device__ __forceinline__ uint32_t fresh_lane() { uint32_t l; asm volatile("mov.u32 %0, %%laneid;" : "=r"(l)); return l; }
__device__ __forceinline__ uint32_t frag_offset(int warp) {
  const uint32_t l = fresh_lane();
  return ((warp & 3) * 16 + (l & 15)) * 128 + (((l >> 4) ^ (l & 7)) << 4);
}
__device__ __forceinline__ bool elect_one() {
  uint32_t p;
  asm volatile("{ .reg .pred q; elect.sync _|q, 0xffffffff; selp.u32 %0, 1, 0, q; }" : "=r"(p));
  return p;
}
__device__ __forceinline__ uint32_t smem_u32(const void* p) { return (uint32_t)__cvta_generic_to_shared(p); }
__device__ __forceinline__ void mbar_init(uint32_t bar, uint32_t cnt) {
  asm volatile("mbarrier.init.shared::cta.b64 [%0], %1;" ::"r"(bar), "r"(cnt) : "memory");
}
__device__ __forceinline__ void mbar_expect_tx(uint32_t bar, uint32_t bytes) {
  asm volatile("mbarrier.arrive.expect_tx.shared::cta.b64 _, [%0], %1;" ::"r"(bar), "r"(bytes) : "memory");
}
__device__ __forceinline__ void mbar_arrive(uint32_t bar) {
  asm volatile("mbarrier.arrive.shared::cta.b64 _, [%0];" ::"r"(bar) : "memory");
}
__device__ __forceinline__ void mbar_arrive_pred(uint32_t bar, bool p) {
  asm volatile("{ .reg .pred p; setp.ne.b32 p, %1, 0; @p mbarrier.arrive.shared::cta.b64 _, [%0]; }" ::"r"(bar), "r"((int)p) : "memory");
}
__device__ __forceinline__ void mbar_arrive_cl(uint32_t bar, uint32_t off, bool p = true) {
  asm volatile("{ .reg .pred p, q; .reg .b32 a; setp.ne.b32 q, %2, 0; setp.ne.and.b32 p, %0, 0, q; add.u32 a, %0, %1; @p mbarrier.arrive.shared::cluster.b64 _, [a]; }"
               ::"r"(bar), "r"(off), "r"((int)p) : "memory");
}
__device__ __forceinline__ uint32_t mapa(uint32_t addr, uint32_t cta) {
  uint32_t r; asm("mapa.shared::cluster.u32 %0, %1, %2;" : "=r"(r) : "r"(addr), "r"(cta)); return r;
}
__device__ __forceinline__ void cluster_arrive() { asm volatile("barrier.cluster.arrive.relaxed.aligned;" ::: "memory"); }
__device__ __forceinline__ void cluster_wait() { asm volatile("barrier.cluster.wait.aligned;" ::: "memory"); }
__device__ __forceinline__ void watchdog(uint32_t& n) {
}
__device__ __forceinline__ void mbar_wait(uint32_t bar, uint32_t parity) {
  asm volatile("{\n.reg .pred p;\nWAIT_%=:\nmbarrier.try_wait.parity.shared::cta.b64 p, [%0], %1;\n@!p bra WAIT_%=;\n}" ::"r"(bar), "r"(parity) : "memory");
}
__device__ __forceinline__ bool mbar_test(uint32_t bar, uint32_t parity) {
  uint32_t ok;
  asm volatile("{\n.reg .pred p;\nmbarrier.test_wait.parity.shared::cta.b64 p, [%1], %2;\nselp.u32 %0, 1, 0, p;\n}" : "=r"(ok) : "r"(bar), "r"(parity) : "memory");
  return ok;
}
__device__ __forceinline__ uint64_t l2_stream() {
  uint64_t f; asm("createpolicy.fractional.L2::evict_first.b64 %0, 1.0;" : "=l"(f)); return f;
}
__device__ __forceinline__ void tma2d(uint32_t dst, const CUtensorMap* m, int c0, int c1, uint32_t bar) {
  asm volatile("cp.async.bulk.tensor.2d.shared::cluster.global.mbarrier::complete_tx::bytes.L2::cache_hint [%0], [%1, {%3, %4}], [%2], %5;"
               ::"r"(dst), "l"(m), "r"(bar), "r"(c0), "r"(c1), "l"(l2_stream()) : "memory");
}
__device__ __forceinline__ void bulk_load(uint32_t dst, const void* src, uint32_t bytes, uint32_t bar) {
  asm volatile("cp.async.bulk.shared::cluster.global.mbarrier::complete_tx::bytes [%0], [%1], %2, [%3];" ::"r"(dst), "l"(src), "r"(bytes), "r"(bar) : "memory");
}
__device__ __forceinline__ void bulk_load_stream(uint32_t dst, const void* src, uint32_t bytes, uint32_t bar) {
  asm volatile("cp.async.bulk.shared::cluster.global.mbarrier::complete_tx::bytes.L2::cache_hint [%0], [%1], %2, [%3], %4;"
               ::"r"(dst), "l"(src), "r"(bytes), "r"(bar), "l"(l2_stream()) : "memory");
}
__device__ __forceinline__ void tma2d_store(const CUtensorMap* m, uint32_t src, int c0, int c1) {
  asm volatile("cp.async.bulk.tensor.2d.global.shared::cta.bulk_group [%0, {%2, %3}], [%1];" ::"l"(m), "r"(src), "r"(c0), "r"(c1) : "memory");
}
__device__ __forceinline__ void bulk_store(void* dst, uint32_t src, uint32_t bytes) {
  asm volatile("cp.async.bulk.global.shared::cta.bulk_group [%0], [%1], %2;" ::"l"(dst), "r"(src), "r"(bytes) : "memory");
}
__device__ __forceinline__ int slice_of(int i) { return i + ((i & 7) == 1) - ((i & 7) == 2); }
__device__ __forceinline__ uint32_t unit_of(uint32_t table, uint32_t i) { return ((table >> (i * 4)) & 15) * UNIT; }
__device__ __forceinline__ void tma3d(uint32_t dst, const CUtensorMap* m, int c0, int c1, int c2, uint32_t bar) {
  asm volatile("cp.async.bulk.tensor.3d.shared::cluster.global.mbarrier::complete_tx::bytes.L2::cache_hint [%0], [%1, {%3, %4, %5}], [%2], %6;"
               ::"r"(dst), "l"(m), "r"(bar), "r"(c0), "r"(c1), "r"(c2), "l"(l2_stream()) : "memory");
}
template <bool STREAM>
__device__ __forceinline__ void tma3d_mc(uint32_t dst, const CUtensorMap* m, int c0, int c1, int c2, uint32_t bar) {
  if (STREAM)
    asm volatile("cp.async.bulk.tensor.3d.shared::cluster.global.mbarrier::complete_tx::bytes.multicast::cluster.L2::cache_hint [%0], [%1, {%3, %4, %5}], [%2], %6, %7;"
                 ::"r"(dst), "l"(m), "r"(bar), "r"(c0), "r"(c1), "r"(c2), "h"((uint16_t)3), "l"(l2_stream()) : "memory");
  else
    asm volatile("cp.async.bulk.tensor.3d.shared::cluster.global.mbarrier::complete_tx::bytes.multicast::cluster [%0], [%1, {%3, %4, %5}], [%2], %6;"
                 ::"r"(dst), "l"(m), "r"(bar), "r"(c0), "r"(c1), "r"(c2), "h"((uint16_t)3) : "memory");
}
__device__ __forceinline__ void prefetch_map(const CUtensorMap* m) {
  asm volatile("prefetch.tensormap [%0];" ::"l"(m) : "memory");
}
__device__ __forceinline__ void fence_async() { asm volatile("fence.proxy.async.global;" ::: "memory"); }
__device__ __forceinline__ void fence_async_smem() { asm volatile("fence.proxy.async.shared::cta;" ::: "memory"); }
__device__ __forceinline__ void bar_sync(int id, int n) { asm volatile("bar.sync %0, %1;" ::"r"(id), "r"(n) : "memory"); }
__device__ __forceinline__ void bar_arrive(int id, int n) { asm volatile("bar.arrive %0, %1;" ::"r"(id), "r"(n) : "memory"); }
__device__ __forceinline__ void wg_fence() { asm volatile("wgmma.fence.sync.aligned;" ::: "memory"); }
__device__ __forceinline__ void wg_commit() { asm volatile("wgmma.commit_group.sync.aligned;" ::: "memory"); }
template <int N> __device__ __forceinline__ void wg_wait() { asm volatile("wgmma.wait_group.sync.aligned %0;" ::"n"(N) : "memory"); }
__device__ __forceinline__ uint64_t make_desc(uint32_t addr, uint32_t lbo, uint32_t sbo) {
  return (uint64_t)((addr & 0x3FFFF) >> 4) | ((uint64_t)(lbo >> 4) << 16) | ((uint64_t)(sbo >> 4) << 32) | (1ull << 62);
}
__device__ __forceinline__ uint32_t ld_relaxed(const uint32_t* p) {
  uint32_t v; asm volatile("ld.relaxed.gpu.global.u32 %0, [%1];" : "=r"(v) : "l"(p) : "memory"); return v;
}
__device__ __forceinline__ uint32_t ld_acquire(const uint32_t* p) {
  uint32_t v; asm volatile("ld.acquire.gpu.global.u32 %0, [%1];" : "=r"(v) : "l"(p) : "memory"); return v;
}
__device__ __forceinline__ uint4 ld_relaxed4(const uint32_t* p) {
  uint4 v; asm volatile("ld.relaxed.gpu.global.v4.u32 {%0,%1,%2,%3}, [%4];" : "=r"(v.x), "=r"(v.y), "=r"(v.z), "=r"(v.w) : "l"(p) : "memory"); return v;
}
__device__ __forceinline__ void st_relaxed(uint32_t* p, uint32_t v) {
  asm volatile("st.relaxed.gpu.global.u32 [%0], %1;" ::"l"(p), "r"(v) : "memory");
}
__device__ __forceinline__ void st_relaxed4(uint32_t* p, uint32_t a, uint32_t b, uint32_t c, uint32_t d) {
  asm volatile("st.relaxed.gpu.global.v4.u32 [%0], {%1,%2,%3,%4};" ::"l"(p), "r"(a), "r"(b), "r"(c), "r"(d) : "memory");
}
__device__ __forceinline__ void st_b128(uint32_t* p, uint32_t a, uint32_t b, uint32_t c, uint32_t d) {
  asm volatile("{ .reg .b64 u, v; .reg .b128 w; mov.b64 u, {%1, %2}; mov.b64 v, {%3, %4}; mov.b128 w, {u, v}; st.relaxed.gpu.global.b128 [%0], w; }"
               ::"l"(p), "r"(a), "r"(b), "r"(c), "r"(d) : "memory");
}
__device__ __forceinline__ uint4 ld_b128(const uint32_t* p) {
  uint4 r;
  asm volatile("{ .reg .b64 u, v; .reg .b128 w; ld.relaxed.gpu.global.b128 w, [%4]; mov.b128 {u, v}, w; mov.b64 {%0, %1}, u; mov.b64 {%2, %3}, v; }"
               : "=r"(r.x), "=r"(r.y), "=r"(r.z), "=r"(r.w) : "l"(p) : "memory");
  return r;
}
__device__ __forceinline__ void st_pairs(uint32_t* p, uint32_t a, uint32_t b, uint32_t tag) {
  asm volatile("{ .reg .b64 u, v; mov.b64 u, {%1, %3}; mov.b64 v, {%2, %3}; st.relaxed.gpu.global.v2.b64 [%0], {u, v}; }"
               ::"l"(p), "r"(a), "r"(b), "r"(tag) : "memory");
}
__device__ __forceinline__ uint4 ld_pairs(const uint32_t* p) {
  uint4 v;
  asm volatile("{ .reg .b64 u, v; ld.relaxed.gpu.global.v2.b64 {u, v}, [%4]; mov.b64 {%0, %1}, u; mov.b64 {%2, %3}, v; }"
               : "=r"(v.x), "=r"(v.y), "=r"(v.z), "=r"(v.w) : "l"(p) : "memory");
  return v;
}
__device__ __forceinline__ uint2 ld_pair(const uint32_t* p) {
  uint2 v;
  asm volatile("{ .reg .b64 u; ld.relaxed.gpu.global.b64 u, [%2]; mov.b64 {%0, %1}, u; }" : "=r"(v.x), "=r"(v.y) : "l"(p) : "memory");
  return v;
}
__device__ __forceinline__ void red_release(uint32_t* p, uint32_t v) {
  asm volatile("red.release.gpu.global.add.u32 [%0], %1;" ::"l"(p), "r"(v) : "memory");
}
__device__ __forceinline__ uint32_t ldg_nc1(const void* p) {
  uint32_t v;
  asm volatile("ld.global.nc.u32 %0, [%1];" : "=r"(v) : "l"(p));
  return v;
}
__device__ __forceinline__ uint4 ldg_nc4(const void* p) {
  uint4 v; asm volatile("ld.global.nc.L1::no_allocate.v4.u32 {%0,%1,%2,%3}, [%4];" : "=r"(v.x), "=r"(v.y), "=r"(v.z), "=r"(v.w) : "l"(p)); return v;
}
__device__ __forceinline__ uint4 ldg_stream4(const void* p) {
  uint4 v;
  asm volatile("ld.global.nc.L1::no_allocate.L2::cache_hint.v4.u32 {%0,%1,%2,%3}, [%4], %5;" : "=r"(v.x), "=r"(v.y), "=r"(v.z), "=r"(v.w) : "l"(p), "l"(l2_stream()));
  return v;
}
__device__ __forceinline__ void stg4(void* p, uint4 v) {
  asm volatile("st.global.v4.u32 [%0], {%1,%2,%3,%4};" ::"l"(p), "r"(v.x), "r"(v.y), "r"(v.z), "r"(v.w) : "memory");
}
__device__ __forceinline__ void wait_counter(const uint32_t* p, uint32_t target) {
  uint32_t n = 0;
  while (__any_sync(0xffffffffu, (int)(ld_acquire(p) - target) < 0)) { watchdog(n); }
}
__device__ __forceinline__ uint32_t tagf(float v, uint32_t tag) { return (__float_as_uint(v) & ~3u) | tag; }
__device__ __forceinline__ bool tag_ok(uint4 v, uint32_t tag) { return (((v.x ^ tag) | (v.y ^ tag) | (v.z ^ tag) | (v.w ^ tag)) & 3u) == 0; }
__device__ __forceinline__ float untag_sum(uint32_t a, uint32_t b) { return __uint_as_float(a & ~3u) + __uint_as_float(b & ~3u); }
__device__ __forceinline__ uint4 poll4(const uint32_t* p, uint32_t tag) {
  uint4 v = ld_relaxed4(p);
  uint32_t n = 0;
  while (!__all_sync(0xffffffffu, tag_ok(v, tag))) { v = ld_relaxed4(p); watchdog(n); }
  return v;
}
__device__ __forceinline__ float bf_lo(uint32_t v) { return __uint_as_float(v << 16); }
__device__ __forceinline__ float bf_hi(uint32_t v) { return __uint_as_float(v & 0xffff0000u); }
__device__ __forceinline__ uint32_t pack_bf(float lo, float hi) {
  uint32_t r; asm("cvt.rn.bf16x2.f32 %0, %1, %2;" : "=r"(r) : "f"(hi), "f"(lo)); return r;
}
__device__ __forceinline__ float rbf(float v) { return __uint_as_float(pack_bf(0.f, v) & 0xffff0000u); }
__device__ __forceinline__ uint32_t hmul2(uint32_t a, uint32_t b) {
  uint32_t r; asm("mul.rn.bf16x2 %0, %1, %2;" : "=r"(r) : "r"(a), "r"(b)); return r;
}
__device__ __forceinline__ uint32_t hadd2(uint32_t a, uint32_t b) {
  uint32_t r; asm("add.rn.bf16x2 %0, %1, %2;" : "=r"(r) : "r"(a), "r"(b)); return r;
}
__device__ __forceinline__ uint32_t hsub2(uint32_t a, uint32_t b) {
  uint32_t r; asm("sub.rn.bf16x2 %0, %1, %2;" : "=r"(r) : "r"(a), "r"(b)); return r;
}
__device__ __forceinline__ float rcp(float x) { float r; asm("rcp.approx.ftz.f32 %0, %1;" : "=f"(r) : "f"(x)); return r; }
__device__ __forceinline__ float ex2(float x) { float r; asm("ex2.approx.ftz.f32 %0, %1;" : "=f"(r) : "f"(x)); return r; }
__device__ __forceinline__ void stmatrix4(uint32_t addr, uint32_t a, uint32_t b, uint32_t c, uint32_t d) {
  asm volatile("stmatrix.sync.aligned.m8n8.x4.shared.b16 [%0], {%1,%2,%3,%4};" ::"r"(addr), "r"(a), "r"(b), "r"(c), "r"(d) : "memory");
}
__device__ __forceinline__ void ldmatrix4(uint32_t addr, uint32_t& a, uint32_t& b, uint32_t& c, uint32_t& d) {
  asm volatile("ldmatrix.sync.aligned.m8n8.x4.shared.b16 {%0,%1,%2,%3}, [%4];" : "=r"(a), "=r"(b), "=r"(c), "=r"(d) : "r"(addr) : "memory");
}
__device__ __forceinline__ void ldmatrix4t(uint32_t addr, uint32_t& a, uint32_t& b, uint32_t& c, uint32_t& d) {
  asm volatile("ldmatrix.sync.aligned.m8n8.x4.trans.shared.b16 {%0,%1,%2,%3}, [%4];" : "=r"(a), "=r"(b), "=r"(c), "=r"(d) : "r"(addr) : "memory");
}
__device__ __forceinline__ void mma16816(float (&d)[4], uint32_t a0, uint32_t a1, uint32_t a2, uint32_t a3, uint32_t b0, uint32_t b1) {
  asm volatile("mma.sync.aligned.m16n8k16.row.col.f32.bf16.bf16.f32 {%0,%1,%2,%3}, {%4,%5,%6,%7}, {%8,%9}, {%0,%1,%2,%3};"
               : "+f"(d[0]), "+f"(d[1]), "+f"(d[2]), "+f"(d[3]) : "r"(a0), "r"(a1), "r"(a2), "r"(a3), "r"(b0), "r"(b1));
}
__device__ __forceinline__ void sts1(uint32_t a, uint32_t v) { asm volatile("st.shared.u32 [%0], %1;" ::"r"(a), "r"(v) : "memory"); }
__device__ __forceinline__ uint4 lds4(uint32_t a) {
  uint4 v; asm volatile("ld.shared.v4.u32 {%0,%1,%2,%3}, [%4];" : "=r"(v.x), "=r"(v.y), "=r"(v.z), "=r"(v.w) : "r"(a) : "memory"); return v;
}
__device__ __forceinline__ uint2 lds2(uint32_t a) {
  uint2 v; asm volatile("ld.shared.v2.u32 {%0,%1}, [%2];" : "=r"(v.x), "=r"(v.y) : "r"(a) : "memory"); return v;
}
__device__ __forceinline__ uint32_t lds1(uint32_t a) {
  uint32_t v; asm volatile("ld.shared.u32 %0, [%1];" : "=r"(v) : "r"(a) : "memory"); return v;
}
__device__ __forceinline__ void sts2(uint32_t a, uint32_t x, uint32_t y) { asm volatile("st.shared.v2.u32 [%0], {%1,%2};" ::"r"(a), "r"(x), "r"(y) : "memory"); }
__device__ __forceinline__ void sts4(uint32_t a, uint4 v) {
  asm volatile("st.shared.v4.u32 [%0], {%1,%2,%3,%4};" ::"r"(a), "r"(v.x), "r"(v.y), "r"(v.z), "r"(v.w) : "memory");
}
__device__ __forceinline__ float silu_f(float v) { return __fdividef(v, 1.f + __expf(-v)); }
__device__ __forceinline__ uint32_t hfma2(uint32_t a, uint32_t b, uint32_t c) {
  uint32_t r; asm("fma.rn.bf16x2 %0, %1, %2, %3;" : "=r"(r) : "r"(a), "r"(b), "r"(c)); return r;
}
__device__ __forceinline__ void split_inv(float sd, uint32_t& ih, uint32_t& il) {
  const float inv = rcp(sd);
  ih = pack_bf(inv, inv);
  const float lo = inv - bf_lo(ih);
  il = pack_bf(lo, lo);
}
__device__ __forceinline__ uint32_t ln_norm(uint32_t x, uint32_t mean2, uint32_t ih, uint32_t il) {
  const uint32_t d = hsub2(x, mean2);
  return hfma2(d, ih, hmul2(d, il));
}
__device__ __forceinline__ uint32_t ln_mod(uint32_t x, uint32_t mean2, uint32_t ih, uint32_t il, uint32_t c1, uint32_t sh) {
  return hadd2(hmul2(ln_norm(x, mean2, ih, il), c1), sh);
}

#define R8(a, i) "+f"(a[i]), "+f"(a[i + 1]), "+f"(a[i + 2]), "+f"(a[i + 3]), "+f"(a[i + 4]), "+f"(a[i + 5]), "+f"(a[i + 6]), "+f"(a[i + 7])
#define D64 "{%0,%1,%2,%3,%4,%5,%6,%7,%8,%9,%10,%11,%12,%13,%14,%15,%16,%17,%18,%19,%20,%21,%22,%23,%24,%25,%26,%27,%28,%29,%30,%31," \
            "%32,%33,%34,%35,%36,%37,%38,%39,%40,%41,%42,%43,%44,%45,%46,%47,%48,%49,%50,%51,%52,%53,%54,%55,%56,%57,%58,%59,%60,%61,%62,%63}"
template <int TB>
__device__ __forceinline__ void mma_ss(float (&d)[64], uint64_t da, uint64_t db, int sc) {
  asm volatile("{\n.reg .pred p;\nsetp.ne.b32 p, %66, 0;\n"
               "wgmma.mma_async.sync.aligned.m64n128k16.f32.bf16.bf16 " D64 ", %64, %65, p, 1, 1, 0, %67;\n}"
               : R8(d, 0), R8(d, 8), R8(d, 16), R8(d, 24), R8(d, 32), R8(d, 40), R8(d, 48), R8(d, 56)
               : "l"(da), "l"(db), "r"(sc), "n"(TB));
}
template <int TB>
__device__ __forceinline__ void mma_rs(float (&d)[64], uint32_t a0, uint32_t a1, uint32_t a2, uint32_t a3, uint64_t db, int sc) {
  asm volatile("{\n.reg .pred p;\nsetp.ne.b32 p, %69, 0;\n"
               "wgmma.mma_async.sync.aligned.m64n128k16.f32.bf16.bf16 " D64 ", {%64,%65,%66,%67}, %68, p, 1, 1, %70;\n}"
               : R8(d, 0), R8(d, 8), R8(d, 16), R8(d, 24), R8(d, 32), R8(d, 40), R8(d, 48), R8(d, 56)
               : "r"(a0), "r"(a1), "r"(a2), "r"(a3), "l"(db), "r"(sc), "n"(TB));
}
#define D128 "{%0,%1,%2,%3,%4,%5,%6,%7,%8,%9,%10,%11,%12,%13,%14,%15,%16,%17,%18,%19,%20,%21,%22,%23,%24,%25,%26,%27,%28,%29,%30,%31," \
             "%32,%33,%34,%35,%36,%37,%38,%39,%40,%41,%42,%43,%44,%45,%46,%47,%48,%49,%50,%51,%52,%53,%54,%55,%56,%57,%58,%59,%60,%61,%62,%63," \
             "%64,%65,%66,%67,%68,%69,%70,%71,%72,%73,%74,%75,%76,%77,%78,%79,%80,%81,%82,%83,%84,%85,%86,%87,%88,%89,%90,%91,%92,%93,%94,%95," \
             "%96,%97,%98,%99,%100,%101,%102,%103,%104,%105,%106,%107,%108,%109,%110,%111,%112,%113,%114,%115,%116,%117,%118,%119,%120,%121,%122,%123,%124,%125,%126,%127}"
#define R128(d, e) R8(d, 0), R8(d, 8), R8(d, 16), R8(d, 24), R8(d, 32), R8(d, 40), R8(d, 48), R8(d, 56), \
                   R8(e, 0), R8(e, 8), R8(e, 16), R8(e, 24), R8(e, 32), R8(e, 40), R8(e, 48), R8(e, 56)
__device__ __forceinline__ void mma256_ss(float (&d)[64], float (&e)[64], uint64_t da, uint64_t db, int sc) {
  asm volatile("{\n.reg .pred p;\nsetp.ne.b32 p, %130, 0;\n"
               "wgmma.mma_async.sync.aligned.m64n256k16.f32.bf16.bf16 " D128 ", %128, %129, p, 1, 1, 0, 1;\n}"
               : R128(d, e) : "l"(da), "l"(db), "r"(sc));
}
__device__ __forceinline__ void mma256_rs(float (&d)[64], float (&e)[64], uint32_t a0, uint32_t a1, uint32_t a2, uint32_t a3, uint64_t db) {
  asm volatile("{\n.reg .pred p;\nsetp.ne.b32 p, 1, 0;\n"
               "wgmma.mma_async.sync.aligned.m64n256k16.f32.bf16.bf16 " D128 ", {%128,%129,%130,%131}, %132, p, 1, 1, 1;\n}"
               : R128(d, e) : "r"(a0), "r"(a1), "r"(a2), "r"(a3), "l"(db));
}
template <int N> __device__ __forceinline__ void keep(float (&a)[N]) {
#pragma unroll
  for (int i = 0; i < N; i++) asm volatile("" : "+f"(a[i])::"memory");
}
template <int N> __device__ __forceinline__ void keep(uint32_t (&a)[N]) {
#pragma unroll
  for (int i = 0; i < N; i++) asm volatile("" : "+r"(a[i])::"memory");
}

#define STAMP(idx) do {} while (0)
#define PROF(grp, cond, idx) do {} while (0)

constexpr float SCL2 = 1.4426950408889634f * 0.08838834764831845f;

__device__ __forceinline__ void pack_p(const float (&s)[64], uint32_t (&p)[32]) {
#pragma unroll
  for (int i = 0; i < 32; i++) p[i] = pack_bf(s[2 * i], s[2 * i + 1]);
}

__device__ __forceinline__ void issue_qk(float (&s)[64], uint32_t q0, uint32_t q1, uint32_t kslot) {
  const uint64_t db = make_desc(kslot, 16, 1024), da0 = make_desc(q0, 16, 1024), da1 = make_desc(q1, 16, 1024);
#pragma unroll
  for (int kk = 0; kk < 8; kk++) mma_ss<0>(s, (kk < 4 ? da0 : da1) + (kk & 3) * 2, db + (kk >> 2) * 1024 + (kk & 3) * 2, kk != 0);
}
__device__ __forceinline__ void issue_pv(float (&o)[64], uint32_t (&p)[32], uint32_t vslot, int acc) {
  uint64_t db = make_desc(vslot, 16384, 1024);
#pragma unroll
  for (int kk = 0; kk < 8; kk++)
    mma_rs<1>(o, p[4 * kk], p[4 * kk + 1], p[4 * kk + 2], p[4 * kk + 3], db + kk * 128, kk == 0 ? acc : 1);
}

template <int H>
__device__ __forceinline__ void store_chunk(const float (&a)[64], uint32_t addr) {
#pragma unroll
  for (int i = 8 * H; i < 8 * H + 8; i += 2)
    stmatrix4(addr ^ ((i & 7) << 4), pack_bf(a[4 * i], a[4 * i + 1]), pack_bf(a[4 * i + 2], a[4 * i + 3]),
              pack_bf(a[4 * i + 4], a[4 * i + 5]), pack_bf(a[4 * i + 6], a[4 * i + 7]));
}
template <int H>
__device__ __forceinline__ void store_chunk(const float (&a)[64], float i0, float i1, uint32_t addr) {
#pragma unroll
  for (int i = 8 * H; i < 8 * H + 8; i += 2)
    stmatrix4(addr ^ ((i & 7) << 4), pack_bf(a[4 * i] * i0, a[4 * i + 1] * i0), pack_bf(a[4 * i + 2] * i1, a[4 * i + 3] * i1),
              pack_bf(a[4 * i + 4] * i0, a[4 * i + 5] * i0), pack_bf(a[4 * i + 6] * i1, a[4 * i + 7] * i1));
}
__device__ __forceinline__ float inv_quad_sum(float l) {
  l += __shfl_xor_sync(0xffffffffu, l, 1);
  l += __shfl_xor_sync(0xffffffffu, l, 2);
  return rcp(l);
}

__device__ __forceinline__ void write_table(uint32_t table, bool ca, uint32_t t, const uint4& m0, const uint4& m1) {
  float c0 = untag_sum(m0.x, m1.x), c1 = untag_sum(m0.y, m1.y), c2 = untag_sum(m0.z, m1.z), c3 = untag_sum(m0.w, m1.w);
  if (ca) { c0 = 1.f + rbf(c0); c1 = 1.f + rbf(c1); c2 = 1.f + rbf(c2); c3 = 1.f + rbf(c3); }
  const uint32_t d = table + (t >> 2) * 64 + (t & 1) * 32 + (t & 2) * 2 + (ca ? 0 : 8);
  sts1(d, pack_bf(c0, c1));
  sts1(d + 16, pack_bf(c2, c3));
}

__device__ __forceinline__ void ln_scalars(float mean, float var, float& mb, float& sd) {
  mb = rbf(mean);
  float r; asm("sqrt.approx.ftz.f32 %0, %1;" : "=f"(r) : "f"(rbf(rbf(var) + 1e-5f)));
  sd = rbf(r);
}

__global__ void __cluster_dims__(2, 1, 1) __launch_bounds__(384, 1) fused_kernel(const __grid_constant__ Maps maps, const Ptrs P) {
  extern __shared__ __align__(1024) uint8_t smem_raw[];
  const uint32_t base = smem_u32(smem_raw);
  const int tid = threadIdx.x, lane = tid & 31;
  const int warp = __shfl_sync(0xffffffffu, tid >> 5, 0);
  const int b = blockIdx.x;
  PROF(31, tid == 0, 0);

  if (b >= NMAIN) {
    float* sc = reinterpret_cast<float*>(smem_raw);
    float* red = sc + DM;
    for (int k = tid; k < DM; k += 384) sc[k] = rbf(silu_f(__bfloat162float(P.c[k])));
    __syncthreads();
    if (tid < 256) {
      const int col = 2048 + (b - NMAIN) * 1024 + (tid & 127) * 8, r0 = (tid >> 7) * 512;
      float acc[8];
#pragma unroll
      for (int e = 0; e < 8; e++) acc[e] = 0.f;
#pragma unroll 1
      for (int r = r0; r < r0 + 512; r += HU) {
        uint4 w[HU];
#pragma unroll
        for (int u = 0; u < HU; u++) w[u] = ldg_stream4(P.w_mod + (size_t)(r + u) * NMOD + col);
#pragma unroll
        for (int u = 0; u < HU; u++) {
          float s = sc[r + u];
          acc[0] += s * bf_lo(w[u].x); acc[1] += s * bf_hi(w[u].x); acc[2] += s * bf_lo(w[u].y); acc[3] += s * bf_hi(w[u].y);
          acc[4] += s * bf_lo(w[u].z); acc[5] += s * bf_hi(w[u].z); acc[6] += s * bf_lo(w[u].w); acc[7] += s * bf_hi(w[u].w);
        }
      }
      if (tid >= 128) {
#pragma unroll
        for (int e = 0; e < 8; e++) red[(tid & 127) * 8 + e] = acc[e];
      }
      const uint32_t tag = ld_relaxed(&g_epoch) % 3 + 1;
      bar_sync(1, 256);
      if (tid < 128) {
        uint32_t o[8];
#pragma unroll
        for (int e = 0; e < 8; e++) o[e] = __float_as_uint(rbf(acc[e] + red[tid * 8 + e])) | tag;
        st_relaxed4(g_mod + col, o[0], o[1], o[2], o[3]);
        st_relaxed4(g_mod + col + 4, o[4], o[5], o[6], o[7]);
        const uint4 wr = ldg_nc4(P.w_r + tid * 8);
        const uint32_t wv[4] = {wr.x, wr.y, wr.z, wr.w};
        float dsum = 0.f;
#pragma unroll
        for (int e = 0; e < 8; e++) {
          const float m = bf_hi(o[e]);
          dsum += (b == NMAIN + 2 ? rbf(1.f + m) : m) * ((e & 1) ? bf_hi(wv[e >> 1]) : bf_lo(wv[e >> 1]));
        }
#pragma unroll
        for (int k = 16; k > 0; k >>= 1) dsum += __shfl_xor_sync(0xffffffffu, dsum, k);
        if (lane == 0) st_relaxed(g_mod + (b - NMAIN) * 4 + warp, tagf(dsum, tag));
      }
    }
    PROF(2, tid == 0, 1);
    return;
  }

  const int rank = b & 1;
  const int rb = ((b >> 4) << 1) | rank, cj = (b >> 1) & 7;
  const bool late = b & 4;
  const uint32_t bfull = base + OFF_BAR, bempty = bfull + NSLOT * 8;
  const uint32_t gfull = bempty + NSLOT * 8, gempty = gfull + 32;
  const uint32_t bar_ofull = gempty + 32;
  const uint32_t bar_ofree = bar_ofull + 32;
  const uint32_t bar_par = bar_ofree + 32;
  const uint32_t bar_mod = bar_par + 8;
  const uint32_t bar_pread = bar_mod + 8;
  const uint32_t bar_xres = bar_pread + 8;
  const uint32_t bar_ring = bar_xres + 8;
  const uint32_t bar_box = bar_ring + 24;
  const uint32_t bar_go = bar_box + 96;
  const uint32_t bar_go2 = bar_go + 16;
  const uint32_t bar_cnt = bar_go + 24;
  const uint32_t xfull = bar_go + 40, xempty = xfull + 32;
  const uint32_t bar_hw = xempty + 32, bar_hx = bar_hw + 8;
  const uint32_t bar_hpub = bar_hx + 16;
  const uint32_t bar_win = bar_hpub + 16;
  const uint32_t bar_rx = bar_win + 8;
  const uint32_t bar_sel = bar_rx + 8;
  const uint32_t bar_gate = bar_sel + 8;
  const uint32_t bar_rel = bar_gate + 8;
  const uint32_t bar_od = bar_rel + 8;
  const uint32_t bar_mod2 = bar_od + 8;
  const uint32_t bar_res = bar_go + 8;
  const uint32_t stage = base + OFF_STAGE, par = base + OFF_PAR;

  if (warp == 10 && elect_one()) prefetch_map(&maps.wm);
  if (warp == 8 && elect_one()) {
    for (int s = 0; s < NSLOT; s++) { mbar_init(bfull + s * 8, 1); mbar_init(bempty + s * 8, 16); }
    for (int s = 0; s < 4; s++) { mbar_init(gfull + s * 8, 1); mbar_init(gempty + s * 8, 16); mbar_init(xfull + s * 8, 1); mbar_init(xempty + s * 8, 8); mbar_init(bar_ofree + s * 8, 1); mbar_init(bar_ofull + s * 8, 128); }
    mbar_init(bar_par, 64); mbar_init(bar_mod, 256); mbar_init(bar_pread, 2); mbar_init(bar_xres, 1);
    mbar_init(bar_ring, 8); mbar_init(bar_ring + 8, 8); mbar_init(bar_ring + 16, 8);
    mbar_init(bar_go, 1); mbar_init(bar_go2, 1); mbar_init(bar_cnt, 1); mbar_init(bar_cnt + 8, 1); mbar_init(bar_hpub, 8); mbar_init(bar_hpub + 8, 8); mbar_init(bar_res, 1); mbar_init(bar_win, 1); mbar_init(bar_rx, 1); mbar_init(bar_sel, 64); mbar_init(bar_gate, 8); mbar_init(bar_rel, 8); mbar_init(bar_od, 1); mbar_init(bar_mod2, 64);
    for (int s = 0; s < 12; s++) mbar_init(bar_box + s * 8, 1);
    asm volatile("fence.mbarrier_init.release.cluster;" ::: "memory");
    prefetch_map(&maps.x); prefetch_map(&maps.wq); prefetch_map(&maps.k); prefetch_map(&maps.v);
  }
  if (warp == 9 && elect_one()) {
    mbar_init(bar_hw, 1); mbar_init(bar_hx, 1); mbar_init(bar_hx + 8, 1);
    asm volatile("fence.mbarrier_init.release.cluster;" ::: "memory");
    mbar_expect_tx(bar_hw, 32768);
    mbar_expect_tx(bar_hx, 16384);
    mbar_expect_tx(bar_hx + 8, 16384);
    const __nv_bfloat16* xs = P.x + (size_t)(rb * 128 + cj * 16) * DM;
    bulk_load(base + 2 * GST_BYTES, xs, 16384, bar_hx);
    if (!late) {
      tma2d(stage, &maps.wm, (b >> 1) * 32, rank * 512, bar_hw);
      tma2d(stage + 16384, &maps.wm, (b >> 1) * 32, rank * 512 + 256, bar_hw);
    }
    bulk_load(base + 3 * GST_BYTES, xs + 8 * DM, 16384, bar_hx + 8);
  }
  cluster_arrive();

  if (warp >= 8) {
    asm volatile("setmaxnreg.dec.sync.aligned.u32 40;");
    if (warp < 10) bar_arrive(1, 320);
    const uint32_t epoch = ld_relaxed(&g_epoch);
    cluster_wait();
    if (warp == 8) {
      const int kvrow = (cj >> 1) * SK + (SK - WIN);
      int wch = cj * 8 + rank * 2;
#pragma unroll 1
      for (int ps = 0; ps < 3; ps++) {
        const CUtensorMap* mw = ps == 2 ? &maps.wo : &maps.wq;
        const uint32_t xt = ps == 1 ? XT1 : XT2, wt = ps == 0 ? WT0 : (ps == 1 ? WT1 : WT2);
        const int nst = ps == 2 ? 32 : 16;
#pragma unroll 1
        for (int i = 0; i < nst; i++) {
          const uint32_t bf = gfull + (i & 3) * 8;
          const int kt = ps == 2 ? (((cj & 1) * 4 + ((i >> 1) & 3)) * 4 + (i >> 3)) * 2 + (i & 1) : (ps ? i : slice_of(i) + (b & 14)) & 15;
          const uint32_t wd = base + unit_of(wt, i & 3) + rank * UNIT, xd = base + unit_of(xt, i & 3);
          const uint8_t* xs = g_act + (uint32_t)(rb * 80 + (ps - 1) * 16 + kt) * UNIT;
          if (ps == 0 && i == HD) mbar_wait(bar_mod, 0);
          const bool xfirst = ps && i < 2;
          if (ps == 2 && i == 0) mbar_wait(bar_ofree + 24, 0);
          if (i == 0) fence_async();
          mbar_wait(gempty + (i & 3) * 8, ((i >> 2) & 1) ^ 1);
          if (elect_one()) {
            mbar_expect_tx(bf, ps ? GST_BYTES : 2 * UNIT);
            if (xfirst) bulk_load_stream(xd, xs, UNIT, bf);
          }
          if (ps && i < 4) mbar_wait(bempty + i * 8, 1);
          if (elect_one()) tma3d_mc<true>(wd, mw, 0, (i == 31 ? kt ^ (rank * 32) : kt) * 64, i == 31 ? cj * 2 : wch, bf);
          if (ps) {
            if (i == 16 || i == 24) { mbar_wait(bar_cnt + i - 16, 0); fence_async(); }
            if (i == RES0) mbar_wait(bar_res, 0);
            if (i == 2) mbar_wait(bar_ofree + (ps - 1) * 16, 0);
            if (elect_one()) {
              if (i == 31) bulk_load(xd, xs, UNIT, bf); else if (!xfirst) bulk_load_stream(xd, xs, UNIT, bf);
              mbar_arrive_pred(bar_go, i == GOST - 1);
              mbar_arrive_pred(bar_go2, ps == 1 && i == PG0);
              mbar_arrive_pred(bar_od, i == (ps == 1 ? ODS1 : ODS));
              if (i == RES0) mbar_expect_tx(bar_xres, 32768);
              if (i == RES0 || i == RES1) tma2d(base + OFF_RES + (i == RES1) * UNIT, &maps.x, cj * 128 + (i == RES1) * 64, rb * 128, bar_xres);
            }
          }
        }
        if (ps == 2) break;
        wch = ps ? ((wch >> 3) ^ rank) * 2 : wch + 4;
#pragma unroll 1
        for (int u = 0; u < 16; u++) {
          const bool isk = (u == 0) || ((u & 1) && u < 15);
          const int blk = (isk ? (u + 1) >> 1 : (u == 15 ? 7 : (u >> 1) - 1)) & 3;
          const uint32_t sl = base + unit_of(ps ? AT1 : AT0, u & 3) + rank * UNIT, bf = bfull + (u & 3) * 8;
          if (u < 4) mbar_wait(gempty + ((u + 1) >> 1) * 8, 1);
          mbar_wait(bempty + (u & 3) * 8, ((u >> 2) & 1) ^ 1);
          if (elect_one()) {
            mbar_expect_tx(bf, SLOT_BYTES);
            if (ps && u >= 7 && u != 8) tma3d_mc<true>(sl, isk ? &maps.k : &maps.v, 0, kvrow + blk * 128, rank, bf);
            else tma3d_mc<false>(sl, isk ? &maps.k : &maps.v, 0, kvrow + blk * 128, rank, bf);
          }
        }
      }
      if (elect_one()) mbar_expect_tx(bar_rx, UNIT);
      mbar_wait(bar_rel, 0);
      if (elect_one()) {
        bulk_load_stream(base + UNIT, g_act + (uint32_t)(rb * 80 + 16 + 63 - (cj & 1) * 32) * UNIT, UNIT, bar_rx);
      }
      if (b < NFFN) {
#pragma unroll 1
        for (int u = 0; u < 12; u++) {
          const uint32_t dst = base + unit_of(u < 4 ? FT_G : (u < 8 ? FT_U : FT_D), u & 3);
          if (elect_one()) mbar_expect_tx(bar_box + u * 8, UNIT);
          if (u == 0 || u == 2 || u == 8) mbar_wait(bar_ring + (u == 8 ? 16 : u * 4), 0);
          const int fp = u < 8 ? FPACE0 : FPACE;
          if (u >= fp) mbar_wait(bar_box + (u - fp) * 8, 0);
          if (elect_one()) {
            if (u < 8) tma2d(dst, u < 4 ? &maps.wg : &maps.wu, b * 32, (u & 3) * 256, bar_box + u * 8);
            else tma3d(dst, &maps.wd, 0, b * 32, (u - 8) * 4, bar_box + u * 8);
          }
        }
      }
    } else if (warp == 9) {
      const uint32_t target = 8 * (epoch + 1);
      uint32_t hmask = 0;
#pragma unroll 1
      for (int i = 0; i < 16; i++) {
        if (i == HDX) mbar_wait(bar_mod, 0);
        const int kt = (2 * cj + slice_of(i)) & 15;
        const uint32_t need = i == 15 ? 0xffffu : 1u << kt;
        if (i >= NRS && (hmask & need) != need) {
          uint32_t n = 0;
          do { hmask = __ballot_sync(0xffffffffu, ld_acquire(&g_cnt_h[rb * 32 + (lane & 15)]) == epoch + 1); watchdog(n); } while ((hmask & need) != need);
          PROF(1, lane == 0 && i == NRS, 26);
          fence_async();
        }
        mbar_wait(xempty + (i & 3) * 8, ((i >> 2) & 1) ^ 1);
        if (elect_one()) {
          mbar_expect_tx(xfull + (i & 3) * 8, UNIT);
          if (i < NRS) tma2d(base + (i & 3) * GST_BYTES, &maps.x, kt * 64, rb * 128, xfull + (i & 3) * 8);
          else bulk_load_stream(base + (i & 3) * GST_BYTES, g_act + (uint32_t)(rb * 80 + kt) * UNIT, UNIT, xfull + (i & 3) * 8);
        }
      }
      prefetch_map(&maps.wo);
#pragma unroll 1
      for (int t = 0; t < 4; t++) {
        if (t & 1) mbar_wait(bar_od, t >> 1);
        const int ops = OPS >> (t & 1);
#pragma unroll 1
        for (int p = 0; p < 32768; p += ops) {
          const uint32_t w = p >> 14, c = (p >> 13) & 1, off = w * 8192 + (p & 8191);
          mbar_wait(bar_ofull + (t & 1) * 16 + w * 8, t >> 1);
          if (elect_one()) {
            bulk_store(g_act + (uint32_t)(rb * 80 + 16 + (cj * 4 + t) * 2 + c) * UNIT + off, base + unit_of(QT, 2 * t + c) + off, ops);
            asm volatile("cp.async.bulk.commit_group;" ::: "memory");
            asm volatile("cp.async.bulk.wait_group.read 0;" ::: "memory");
          }
        }
        if (elect_one()) {
          mbar_arrive(t < 3 ? bar_ofree + t * 8 : bar_res);
          asm volatile("cp.async.bulk.wait_group 0;" ::: "memory");
          fence_async();
          red_release(&g_cnt_o[((rb * 4 + t) * 2 + (cj >> 2)) * 32], 2);
        }
        if (t) {
          wait_counter(&g_cnt_o[(rb * 8 + 2 * t + (cj & 1)) * 32], target);
          if (t & 1) wait_counter(&g_cnt_o[(rb * 8 + (t == 1 ? cj & 1 : 7 - (cj & 1))) * 32], target);
          if (elect_one()) mbar_arrive(t == 1 ? bar_ofree + 24 : bar_cnt + t * 8 - 16);
        }
      }
      PROF(2, lane == 0, 27);
      const uint32_t tag = epoch % 3 + 1;
      const uint32_t* inbox = g_cand + (b >> 1) % CR * 512 + (lane & 15) * CS;
      mbar_wait(bar_ring + 16, 0);
      uint32_t c0 = ld_relaxed(inbox), n = 0;
#define CAND_STEP(cv)                                                                                        \
      {                                                                                                      \
        const bool valid = (cv & 3u) == tag, all = __all_sync(0xffffffffu, valid);                           \
        const uint32_t best = __reduce_max_sync(0xffffffffu, valid ? cv : 0u);                               \
        const uint32_t blk = __ffs(__ballot_sync(0xffffffffu, cv == best)) - 1;                              \
        if (best) sts2(par + PAR_CONST + 56, best, (blk << 7 | (~best >> 2 & 127)) | (all ? 0x1800 : 0x800)); \
        if (all) break;                                                                                      \
        cv = ld_relaxed(inbox);                                                                              \
      }
      while (true) { CAND_STEP(c0) watchdog(n); }
    } else {
      const int t2 = tid - 320;
      if (late && warp == 10) {
        mbar_wait(bar_hx, 0);
        if (elect_one()) {
          tma2d(stage, &maps.wm, (b >> 1) * 32, rank * 512, bar_hw);
          tma2d(stage + 16384, &maps.wm, (b >> 1) * 32, rank * 512 + 256, bar_hw);
        }
      }
      {
        const uint32_t tag = epoch % 3 + 1;
        mbar_wait(bar_hx + 8, 0);
        mbar_wait(bar_hw, 0);
        __nanosleep(late ? OSL2 : OSL);
        {
          const uint32_t t7 = (warp & 1) * 64 + (lane >> 4) * 32 + 16 + (lane & 15);
          const uint32_t* pm = g_modp + ((cj * 128 + t7 * 4) & (DM - 1));
          uint4 m0, m1, m2, m3;
          uint32_t n = 0;
          do {
            m0 = ld_relaxed4(pm); m1 = ld_relaxed4(pm + 2 * DM); m2 = ld_relaxed4(pm + DM); m3 = ld_relaxed4(pm + 3 * DM);
            watchdog(n);
          } while (!__all_sync(0xffffffffu, tag_ok(m0, tag) && tag_ok(m1, tag) && tag_ok(m2, tag) && tag_ok(m3, tag)));
          write_table(par, false, t7, m0, m1);
          write_table(par, true, t7, m2, m3);
          mbar_arrive(bar_mod2);
        }
      }
      mbar_wait(bar_hpub + (warp & 1) * 8, 0);
      PROF(1, t2 == 0, 24);
#pragma unroll 1
      for (int c = 0; c < 8; c++) {
        const uint32_t off = (warp & 1) * UNIT + c * 2048 + lane * 16;
        uint8_t* dst = g_act + (uint32_t)(rb * 80 + cj * 2) * UNIT + off;
        const uint4 v0 = lds4(stage + off), v1 = lds4(stage + off + 512), v2 = lds4(stage + off + 1024), v3 = lds4(stage + off + 1536);
        stg4(dst, v0); stg4(dst + 512, v1); stg4(dst + 1024, v2); stg4(dst + 1536, v3);
      }
      __syncwarp();
      PROF(1, t2 == 0, 15);
      if (lane == 0) {
        mbar_arrive(bar_pread);
        red_release(&g_cnt_h[rb * 32 + cj * 2 + (warp & 1)], 1);
        PROF(1, t2 == 0, 25);
        prefetch_map(&maps.wg); prefetch_map(&maps.wu); prefetch_map(&maps.wd); prefetch_map(&maps.out);
      }
      __syncwarp();
      if (b < NFFN) {
        mbar_wait(bar_go2, 0);
        const __nv_bfloat16* pg = ((b & 1) ? P.w_up : P.w_gate) + (b >> 1) * 64 + (size_t)t2 * FF;
        const __nv_bfloat16* pd = P.w_down + (size_t)b * 32768 + t2 * 64;
        PROF(2, t2 == 0, 13);
#pragma unroll 1
        for (int i = 0; i < WN; i += WB) {
          uint32_t v[WB];
#pragma unroll
          for (int u = 0; u < WB; u++) {
            const int k = i + u;
            asm volatile("ld.global.cg.L2::128B.u32 %0, [%1];" : "=r"(v[u]) : "l"(k < 16 ? pg + (size_t)k * 64 * FF : pd + (k - 16) * 4096));
          }
#pragma unroll
          for (int u = 1; u < WB; u++) v[0] ^= v[u];
          sts1(par + PAR_SINK + t2 * 4, v[0]);
        }
        PROF(2, t2 == 0, 14);
      }
      const uint32_t tag = epoch % 3 + 1;
      mbar_wait(bar_go, 0);
      bar_sync(4, 64);
      if (warp == 10) {
        const uint32_t* src = g_mod + 2 * DM + cj * 128 + lane * 4;
        const uint2 wr = *reinterpret_cast<const uint2*>(P.w_r + cj * 128 + lane * 4);
        uint4 vga, vsb, vcb, vgb;
        uint32_t n = 0;
        do {
          vga = ld_relaxed4(src); vsb = ld_relaxed4(src + DM); vcb = ld_relaxed4(src + 2 * DM); vgb = ld_relaxed4(src + 3 * DM);
          watchdog(n);
        } while (!__all_sync(0xffffffffu, tag_ok(vga, tag) && tag_ok(vsb, tag) && tag_ok(vcb, tag) && tag_ok(vgb, tag)));
        const float c0 = rbf(1.f + bf_hi(vcb.x)), c1 = rbf(1.f + bf_hi(vcb.y)), c2 = rbf(1.f + bf_hi(vcb.z)), c3 = rbf(1.f + bf_hi(vcb.w));
        const float a0 = c0 * bf_lo(wr.x), a1 = c1 * bf_hi(wr.x), a2 = c2 * bf_lo(wr.y), a3 = c3 * bf_hi(wr.y);
        const uint32_t h0 = pack_bf(a0, a1), h1 = pack_bf(a2, a3);
        const uint32_t t1 = par + PAR_T1 + (lane >> 2) * 64 + (lane & 1) * 32 + (lane & 2) * 2;
        sts1(t1, h0); sts1(t1 + 8, pack_bf(a0 - bf_lo(h0), a1 - bf_hi(h0)));
        sts1(t1 + 16, h1); sts1(t1 + 24, pack_bf(a2 - bf_lo(h1), a3 - bf_hi(h1)));
        const uint32_t tg = par + PAR_SINK + (lane >> 3) * 64 + (lane & 1) * 32 + (lane & 6) * 2;
        sts1(tg, __byte_perm(vga.x, vga.y, 0x7632)); sts1(tg + 16, __byte_perm(vga.z, vga.w, 0x7632));
        sts4(par + PAR_T2 + lane * 32, make_uint4(pack_bf(c0, c1), __byte_perm(vsb.x, vsb.y, 0x7632), __byte_perm(vgb.x, vgb.y, 0x7632), __byte_perm(vga.x, vga.y, 0x7632)));
        sts4(par + PAR_T2 + lane * 32 + 16, make_uint4(pack_bf(c2, c3), __byte_perm(vsb.z, vsb.w, 0x7632), __byte_perm(vgb.z, vgb.w, 0x7632), __byte_perm(vga.z, vga.w, 0x7632)));
      } else {
        const uint4 g = poll4((lane & 8) ? g_mod + 8 - (lane & 1) * 4 : g_mod + 5 * DM + (b >> 4) * 128 + (lane & 7) * 16 + (b & 12), tag);
        sts1(par + PAR_CONST + 60, 0);
        if (lane < 8) sts1(par + PAR_CONST + 16 + lane * 4, (b & 2) ? ((b & 1) ? g.w : g.z) : ((b & 1) ? g.y : g.x));
        else if (lane < 10) sts2(par + PAR_CONST + (lane - 8) * 8, __float_as_uint(untag_sum(g.x, g.y) + untag_sum(g.z, g.w)), epoch);
      }
      __syncwarp();
#pragma unroll 1
      for (int q = 0; q < 32; q++) {
        st_b128(g_xch + ((size_t)b * 8 * 256 + q * 64 + t2) * 4, (epoch & 1) << 16, 0, 0, 0);
        __nanosleep(RSL);
      }
      for (int q = 0; q < 2; q++) st_relaxed4(g_stats + ((size_t)cj * SEQ + rb * 128 + q * 64 + t2) * 4, 0, 0, 0, 0);
      if (b < NFFN)
        for (int q = 0; q < 2; q++) st_relaxed4(ypart_slot(b, q * 64 + t2), 0, 0, 0, 0);
      st_relaxed4(g_row + rb * 2 * DM + (t2 >> 5) * DM + cj * 128 + (t2 & 31) * 4, 0, 0, 0, 0);
      __threadfence();
      mbar_arrive(bar_par);
      mbar_wait(bar_gate, 0);
      uint32_t have = 0, n = 0;
      while (true) {
        const uint32_t st = lds1(par + PAR_CONST + 60) >> 7;
        if ((st & 31) != have) {
          const uint32_t* hsrc = g_row + (st & 15) * 2 * DM + t2 * 4;
          uint4 hv[4];
          bool ok = true;
#pragma unroll
          for (int i = 0; i < 4; i++) hv[i] = ld_pairs(hsrc + i * 256);
#pragma unroll
          for (int i = 0; i < 4; i++) {
            sts2(base + ((FT_G >> i * 4) & 15) * UNIT + (warp & 1) * 8192 + 256 + lane * 8, hv[i].x, hv[i].z);
            ok = ok && hv[i].y == tag && hv[i].w == tag;
          }
          have = __all_sync(0xffffffffu, ok) ? st & 31 : 0;
        }
        if ((st ^ have) == 32) break;
        watchdog(n);
      }
      mbar_arrive(bar_sel);
    }
    __syncwarp();
    cluster_arrive();
    {
      const uint32_t tag = epoch % 3 + 1, t3 = tid - 256;
      mbar_wait(bar_win, 0);
      uint2 win = lds2(par + PAR_CONST + 56);
      win.y &= 0x7ff;
      const uint32_t* fsrc = g_row + (win.y >> 7) * 2 * DM + (b >> 4) * 128 + (t3 & 7) * 16 + (b & 6) * 2 + ((b >> 2) & 2);
      const uint32_t* ysrc = ypart_slot(min(t3, NFFN - 1), b);
      uint2 fh = ld_pair(fsrc), fx = ld_pair(fsrc + DM);
      uint4 ya = ld_b128(ysrc);
      const float rwin = __uint_as_float(((int)win.x < 0 ? win.x & 0x7fffffffu : ~win.x) & ~0x1ffu);
      const float rs = rbf(rcp(1.f + __expf(-rbf(rwin))));
      uint32_t n = 0;
      while (__any_sync(0xffffffffu, fh.y != tag || fx.y != tag)) { fh = ld_pair(fsrc); fx = ld_pair(fsrc + DM); watchdog(n); }
      while (true) {
        const bool miss = ((ya.x & 1) | (ya.y & 1) << 1) != tag;
        if (!__any_sync(0xffffffffu, miss)) break;
        if (miss) ya = ld_b128(ysrc);
        watchdog(n);
      }
      PROF(8, t3 == 0, 5);
      float y[8] = {bf_lo(ya.x & ~1u), bf_hi(ya.x), bf_lo(ya.y & ~1u), bf_hi(ya.y), bf_lo(ya.z), bf_hi(ya.z), bf_lo(ya.w), bf_hi(ya.w)};
#pragma unroll
      for (int h = 4; h > 0; h >>= 1) {
        const bool up = lane & (h * 2);
#pragma unroll
        for (int e = 0; e < h; e++) y[e] = (up ? y[e + h] : y[e]) + __shfl_xor_sync(0xffffffffu, up ? y[e] : y[e + h], h * 2);
      }
      y[0] += __shfl_xor_sync(0xffffffffu, y[0], 1);
      if (!(lane & 1)) sts1(par + PAR_RED + 64 + t3 * 2, __float_as_uint(y[0]));
      bar_sync(4, 128);
      if (t3 < 8) {
        float y0 = 0.f;
#pragma unroll
        for (int w7 = 0; w7 < 7; w7++) y0 += __uint_as_float(lds1(par + PAR_RED + 64 + w7 * 32 + t3 * 4));
        const uint32_t gv = lds1(par + PAR_CONST + 16 + t3 * 4);
        const uint32_t upd = hmul2(pack_bf(y0, y0), pack_bf(rs, rs));
        const uint32_t r = hadd2(fx.x, hmul2(__byte_perm(gv, gv, 0x3232), hadd2(fh.x, upd)));
        reinterpret_cast<uint16_t*>(P.out)[(size_t)win.y * DM + (b >> 4) * 128 + t3 * 16 + (b & 15)] = (b & 1) ? r >> 16 : r;
        if (b == 0 && t3 == 0) st_relaxed(&g_epoch, epoch + 1);
      }
      PROF(31, t3 == 0, 36);
    }
    cluster_wait();
  } else {
    const int wg = warp >> 2;

    uint32_t tag;
    {
      uint32_t* const pmod = g_modp + rank * 2 * DM + (b >> 1) * 32 + lane;
      uint32_t* const pln = g_ln1 + (rb * 128 + cj * 16 + warp) * 4;
      uint32_t sc[8];
#pragma unroll
      for (int k = 0; k < 8; k++) sc[k] = ldg_nc1(P.c + rank * 512 + warp * 64 + k * 8 + (lane & 3) * 2);
      const uint32_t epoch = ld_relaxed(&g_epoch);
      if (warp == 0) st_relaxed(pmod, 0);
      if (lane == 0) { st_b128(pln, 0, 0, 0, 0); st_b128(pln + 32, 0, 0, 0, 0); }
      asm volatile("setmaxnreg.inc.sync.aligned.u32 232;");
      bar_sync(1, 320);
#pragma unroll
      for (int k = 0; k < 8; k++) sc[k] = pack_bf(silu_f(bf_lo(sc[k])), silu_f(bf_hi(sc[k])));
      keep(sc);
      tag = epoch % 3 + 1;
#pragma unroll
      for (int part = 0; part < 4; part++) {
        if (!(part & 1)) {
          const uint32_t xa = base + (2 + part / 2) * GST_BYTES + warp * 2048 + lane * 16;
          mbar_wait(bar_hx + part * 4, 0);
          float s0 = 0.f, s1 = 0.f, q0 = 0.f, q1 = 0.f;
#pragma unroll
          for (int q = 0; q < 4; q++) {
            const uint4 xv = lds4(xa + q * 512);
            const uint32_t u[4] = {xv.x, xv.y, xv.z, xv.w};
#pragma unroll
            for (int e = 0; e < 4; e++) { const float lo = bf_lo(u[e]), hi = bf_hi(u[e]); s0 += lo; s1 += hi; q0 += lo * lo; q1 += hi * hi; }
          }
          s0 += s1; q0 += q1;
#pragma unroll
          for (int o = 16; o > 0; o >>= 1) { s0 += __shfl_xor_sync(0xffffffffu, s0, o); q0 += __shfl_xor_sync(0xffffffffu, q0, o); }
          const float mean = s0 * (1.f / DM);
          float mb, sd;
          ln_scalars(mean, fmaxf(q0 * (1.f / DM) - mean * mean, 0.f), mb, sd);
          uint32_t ih, il;
          split_inv(sd, ih, il);
          if (lane == 0) st_b128(pln + part * 16, pack_bf(mb, mb), ih, il, tag);
          PROF(1, tid == 0 && part == 2, 4);
        } else if (late == (part == 3)) {
          const uint32_t fr = (lane & 7) + (lane >> 4) * 8, tq = lane & 3;
          const uint32_t wa = stage + warp * 4096 + fr * 64 + ((((lane >> 3) & 1) ^ ((fr >> 1) & 3)) << 4);
          float d0[4] = {0.f, 0.f, 0.f, 0.f}, d1[4] = {0.f, 0.f, 0.f, 0.f};
          mbar_wait(bar_hw, 0);
#pragma unroll
          for (int ks = 0; ks < 4; ks++) {
            uint32_t w[8];
            ldmatrix4t(wa + ks * 1024, w[0], w[1], w[2], w[3]);
            ldmatrix4t((wa ^ 32) + ks * 1024, w[4], w[5], w[6], w[7]);
            mma16816(d0, w[0], w[1], w[2], w[3], sc[2 * ks], sc[2 * ks + 1]);
            mma16816(d1, w[4], w[5], w[6], w[7], sc[2 * ks], sc[2 * ks + 1]);
          }
          sts1(base + 2 * GST_BYTES + warp * 2048 + (tq * 8 + (lane >> 2)) * 4, __float_as_uint((tq & 2) ? ((tq & 1) ? d1[2] : d1[0]) : ((tq & 1) ? d0[2] : d0[0])));
          bar_sync(1, 256);
          if (warp == 0) {
            float s = 0.f;
#pragma unroll
            for (int w8 = 0; w8 < 8; w8++) s += __uint_as_float(lds1(base + 2 * GST_BYTES + w8 * 2048 + lane * 4));
            st_relaxed(pmod, (__float_as_uint(s) & ~3u) | tag);
          }
          PROF(1, tid == 0, 3);
        }
      }
      cluster_wait();
      if (wg == 1) bar_arrive(2, 256);
    }

    float f0 = 0.f, f1 = 0.f;
    const uint32_t rempty = lane < 2 ? mapa(bempty, lane & 1) : 0;
    constexpr uint32_t GE = NSLOT * 8 + 32;
    float o[64], s[64];
#pragma unroll 1
    for (int ps = 0; ps < 3; ps++) {
      {
        const uint32_t xt = ps == 1 ? XT1 : XT2, wt = ps == 1 ? WT1 : WT2;
        const int nst = ps == 2 ? 28 : 14;
        if (ps == 0) {
          float ga[64], gb[64];
#pragma unroll
          for (int i = 0; i < 64; i++) { ga[i] = 0.f; gb[i] = 0.f; }
          uint32_t a[2][16];
          const uint32_t l = fresh_lane();
          uint32_t fa[4];
#pragma unroll
          for (int kk = 0; kk < 4; kk++) fa[kk] = (base + wg * 8192 + frag_offset(warp)) ^ (kk * 32);
          const uint32_t mt = par + (l & 3) * 16;
          auto fetch = [&](int i, uint32_t (&f)[16], uint32_t z) {
            mbar_wait(xfull + (i & 3) * 8, i >> 2);
#pragma unroll
            for (int kk = 0; kk < 4; kk++) ldmatrix4(fa[kk] + (i & 3) * GST_BYTES + z, f[4 * kk], f[4 * kk + 1], f[4 * kk + 2], f[4 * kk + 3]);
          };
          const bool oddw = warp & 2;
          uint4 r0, r1;
          {
            const uint32_t t7 = (warp & 1) * 64 + (l >> 4) * 32 + (l & 15);
            const uint32_t* pm = g_modp + wg * DM + ((cj * 128 + t7 * 4) & (DM - 1));
            const uint32_t* pr = g_ln1 + (rb * 128 + warp * 16 + (l >> 2)) * 4;
            uint4 m0 = make_uint4(tag, tag, tag, tag), m1 = m0;
            if (!oddw) { m0 = ld_relaxed4(pm); m1 = ld_relaxed4(pm + 2 * DM); }
            r0 = ld_b128(pr); r1 = ld_b128(pr + 32);
            fetch(0, a[0], 0); fetch(1, a[1], 0);
            uint32_t n = 0;
            bool written = false;
#pragma unroll 1
            while (true) {
              uint32_t miss;
              asm volatile("{ .reg .pred p0, p1, p2, p3; .reg .b32 t, u;\n"
                           "lop3.b32 t, %1, %2, %19, 0x7e; lop3.b32 u, %3, %4, %19, 0x7e; or.b32 t, t, u; and.b32 t, t, 3; setp.ne.u32 p0, t, 0;\n"
                           "lop3.b32 t, %5, %6, %19, 0x7e; lop3.b32 u, %7, %8, %19, 0x7e; or.b32 t, t, u; and.b32 t, t, 3; setp.ne.u32 p1, t, 0;\n"
                           "setp.ne.u32 p2, %12, %19; setp.ne.u32 p3, %16, %19;\n"
                           "@p0 ld.relaxed.gpu.global.v4.u32 {%1, %2, %3, %4}, [%17];\n"
                           "@p1 ld.relaxed.gpu.global.v4.u32 {%5, %6, %7, %8}, [%17 + 8192];\n"
                           "@p2 ld.relaxed.gpu.global.v4.u32 {%9, %10, %11, %12}, [%18];\n"
                           "@p3 ld.relaxed.gpu.global.v4.u32 {%13, %14, %15, %16}, [%18 + 128];\n"
                           "or.pred p0, p0, p1; or.pred p2, p2, p3; vote.sync.any.pred p0, p0, 0xffffffff; vote.sync.any.pred p2, p2, 0xffffffff;\n"
                           "selp.u32 t, 1, 0, p0; selp.u32 u, 2, 0, p2; or.b32 %0, t, u; }"
                           : "=r"(miss), "+r"(m0.x), "+r"(m0.y), "+r"(m0.z), "+r"(m0.w), "+r"(m1.x), "+r"(m1.y), "+r"(m1.z), "+r"(m1.w),
                             "+r"(r0.x), "+r"(r0.y), "+r"(r0.z), "+r"(r0.w), "+r"(r1.x), "+r"(r1.y), "+r"(r1.z), "+r"(r1.w)
                           : "l"(pm), "l"(pr), "r"(tag) : "memory");
              if (!(miss & 1) && !written) {
                written = true;
                if (!oddw) write_table(par, wg, t7, m0, m1);
                mbar_arrive(bar_mod);
              }
              if (!miss) break;
              watchdog(n);
            }
          }
          const uint32_t zero = r0.w ^ tag;
          auto normalize = [&](uint32_t (&f)[16]) {
#pragma unroll
            for (int k = 0; k < 16; k += 2) { f[k] = ln_norm(f[k], r0.x, r0.y, r0.z); f[k + 1] = ln_norm(f[k + 1], r1.x, r1.y, r1.z); }
          };
          auto modulate = [&](int i, uint32_t (&f)[16]) {
#pragma unroll
            for (int kk = 0; kk < 4; kk++) {
              const uint4 m = lds4(mt + slice_of(i) * 256 + kk * 64);
              f[4 * kk] = hfma2(f[4 * kk], m.x, m.z); f[4 * kk + 1] = hfma2(f[4 * kk + 1], m.x, m.z);
              f[4 * kk + 2] = hfma2(f[4 * kk + 2], m.y, m.w); f[4 * kk + 3] = hfma2(f[4 * kk + 3], m.y, m.w);
            }
            keep(f);
            mbar_arrive_pred(xempty + (i & 3) * 8, l == 0);
          };
          auto publish = [&](int u, uint32_t (&f)[16]) {
#pragma unroll
            for (int kk = 0; kk < 4; kk++) stmatrix4(fa[kk] + OFF_STAGE + u * UNIT, f[4 * kk], f[4 * kk + 1], f[4 * kk + 2], f[4 * kk + 3]);
            __syncwarp();
            mbar_arrive_pred(bar_hpub + u * 8, l == 0);
          };
          auto multiply = [&](int i, uint32_t (&f)[16]) {
            mbar_wait(gfull + (i & 3) * 8, i >> 2);
            const uint64_t db = make_desc(base + (i & 3) * GST_BYTES + UNIT, 8192, 1024);
            wg_fence();
#pragma unroll
            for (int kk = 0; kk < 4; kk++) mma256_rs(ga, gb, f[4 * kk], f[4 * kk + 1], f[4 * kk + 2], f[4 * kk + 3], db + kk * 128);
            wg_commit();
          };
          auto next = [&](int i, uint32_t (&f)[16]) {
            wg_wait<1>();
            mbar_arrive_cl(rempty, GE + ((i + 2) & 3) * 8);
            uint32_t z = zero;
#pragma unroll
            for (int k = 0; k < 16; k += 2) asm volatile("lop3.b32 %0, %1, %2, %0, 0xA8;" : "+r"(z) : "r"(f[k]), "r"(f[k + 1]));
            fetch(i, f, z);
            normalize(f);
            if (i == 2) { keep(f); mbar_wait(bar_mod2, 0); }
            modulate(i, f); multiply(i, f);
          };
          normalize(a[0]); normalize(a[1]);
          keep(a[0]); keep(a[1]);
          mbar_wait(bar_mod, 0);
          PROF(1, tid == 0, 2);
          modulate(0, a[0]); multiply(0, a[0]); publish(0, a[0]);
          modulate(1, a[1]); multiply(1, a[1]);
#pragma unroll 1
          for (int i = 2; i < NRS; i += 2) {
            next(i, a[0]);
            if (i == 2) publish(1, a[0]);
            next(i + 1, a[1]);
          }
          wg_wait<1>();
          mbar_arrive_cl(rempty, GE + ((NRS + 2) & 3) * 8);
#pragma unroll 1
          for (int i = NRS; i < 14; i++) {
            mbar_wait(xfull + (i & 3) * 8, (i >> 2) & 1);
            mbar_wait(gfull + (i & 3) * 8, (i >> 2) & 1);
            const uint32_t xa = base + (i & 3) * GST_BYTES;
            const uint64_t da = make_desc(xa + wg * 8192, 16, 1024), db = make_desc(xa + UNIT, 8192, 1024);
            if (i == 13) bar_sync(2 + wg, 256);
            wg_fence();
#pragma unroll
            for (int kk = 0; kk < 4; kk++) mma256_ss(ga, gb, da + kk * 2, db + kk * 128, 1);
            wg_commit();
            if (i == 13) bar_arrive(3 - wg, 256);
            wg_wait<1>();
            uint32_t z = zero;
#pragma unroll
            for (int k = 0; k < 16; k += 2) asm volatile("lop3.b32 %0, %1, %2, %0, 0xA8;" : "+r"(z) : "r"(a[1][k]), "r"(a[1][k + 1]));
            mbar_arrive_cl(rempty, GE + ((i + 3) & 3) * 8 + z);
            mbar_arrive_pred(xempty + ((i + 3) & 3) * 8, l == 0 && i != NRS);
          }
          mbar_wait(xfull + 16, 1);
          wg_wait<0>();
          keep(ga); keep(gb);
#pragma unroll
          for (int i = 0; i < 64; i++) {
            asm volatile("mov.b32 %0, %1;" : "=f"(s[i]) : "f"(ga[i]));
            asm volatile("mov.b32 %0, %1;" : "=f"(o[i]) : "f"(gb[i]));
          }
        } else {
          float ga[64], gb[64];
#pragma unroll
          for (int i = 0; i < 64; i++) {
            asm volatile("mov.b32 %0, %1;" : "=f"(ga[i]) : "f"(s[i]));
            asm volatile("mov.b32 %0, %1;" : "=f"(gb[i]) : "f"(o[i]));
          }
#pragma unroll 1
          for (int i = 0; i < nst; i++) {
            mbar_wait(gfull + (i & 3) * 8, (i >> 2) & 1);
            const uint64_t da = make_desc(base + unit_of(xt, i & 3) + wg * 8192, 16, 1024), db = make_desc(base + unit_of(wt, i & 3), 8192, 1024);
            if (i == nst - 1) bar_sync(2 + wg, 256);
            wg_fence();
#pragma unroll
            for (int kk = 0; kk < 4; kk++) mma256_ss(ga, gb, da + kk * 2, db + kk * 128, kk ? 1 : i);
            wg_commit();
            if (i == nst - 1) bar_arrive(3 - wg, 256);
            wg_wait<1>();
            mbar_arrive_cl(rempty, GE + ((i + 3) & 3) * 8, i != 0);
            PROF(4, tid == 0 && (i & 3) == 0, 40 + (ps - 1) * 4 + i / 4);
          }
          wg_wait<0>();
          keep(ga); keep(gb);
#pragma unroll
          for (int i = 0; i < 64; i++) {
            asm volatile("mov.b32 %0, %1;" : "=f"(s[i]) : "f"(ga[i]));
            asm volatile("mov.b32 %0, %1;" : "=f"(o[i]) : "f"(gb[i]));
          }
        }
        mbar_arrive_cl(rempty, GE + (ps == 2 ? 24 : 8));
        if (ps == 2) break;
      }
      const uint32_t qw = base + wg * 8192, qt = QT >> (16 * ps), at = ps ? AT1 : AT0;
      {
        const uint32_t wt = ps ? WT1 : WT0;
        const uint64_t da0 = make_desc(qw + unit_of(qt, 2), 16, 1024), da1 = make_desc(qw + unit_of(qt, 3), 16, 1024);
        const uint64_t db0 = make_desc(base + unit_of(wt, 2), 8192, 1024), db1 = make_desc(base + unit_of(wt, 3), 8192, 1024);
        mbar_wait(gfull + 16, 1);
        bar_sync(2 + wg, 256);
        wg_fence();
#pragma unroll
        for (int kk = 0; kk < 4; kk++) mma_ss<1>(s, da0 + kk * 2, db0 + kk * 128, 1);
        wg_commit();
        mbar_wait(xfull + 24, 1);
        mbar_wait(gfull + 24, 1);
        wg_fence();
#pragma unroll
        for (int kk = 0; kk < 4; kk++) mma_ss<1>(s, da1 + kk * 2, db1 + kk * 128, 1);
        wg_commit();
        bar_arrive(3 - wg, 256);
        mbar_wait(ps == 0 ? bar_pread : bar_ofree + 8, 0);
        wg_wait<0>();
        keep(s);
        PROF(2, tid == 0, 8 + ps * 8);
        uint32_t q[32];
        pack_p(s, q);
#pragma unroll
        for (int i = 0; i < 4; i++) stmatrix4((qw + unit_of(qt, 0) + frag_offset(warp)) ^ (i << 5), q[4 * i], q[4 * i + 1], q[4 * i + 2], q[4 * i + 3]);
        keep(q);
        bar_sync(2 + wg, 256);
        wg_fence();
#pragma unroll
        for (int kk = 0; kk < 8; kk++) mma_ss<1>(o, (kk < 4 ? da0 : da1) + (kk & 3) * 2, (kk < 4 ? db0 : db1) + UNIT / 16 + (kk & 3) * 128, 1);
        wg_commit();
        mbar_wait(bfull, 0);
        wg_fence();
        const uint64_t dk = make_desc(base + unit_of(at, 0), 16, 1024);
#pragma unroll
        for (int kk = 0; kk < 8; kk++) mma_rs<0>(s, q[4 * kk], q[4 * kk + 1], q[4 * kk + 2], q[4 * kk + 3], dk + (kk >> 2) * 1024 + (kk & 3) * 2, kk != 0);
        wg_commit();
        bar_arrive(3 - wg, 256);
#pragma unroll
        for (int i = 4; i < 8; i++) stmatrix4((qw + unit_of(qt, 1) + frag_offset(warp)) ^ ((i & 3) << 5), q[4 * i], q[4 * i + 1], q[4 * i + 2], q[4 * i + 3]);
        wg_wait<1>();
        keep(o);
        mbar_arrive_cl(rempty, GE + 16);
        mbar_arrive_cl(rempty, GE + 24);
        store_chunk<0>(o, qw + unit_of(qt, 2) + frag_offset(warp));
        store_chunk<1>(o, qw + unit_of(qt, 3) + frag_offset(warp));
        wg_wait<0>();
        keep(s);
        mbar_arrive_cl(rempty, 0);
      }
      PROF(4, tid == 0 && ps == 1, 61);
      float l0 = 0.f, l1 = 0.f;
      auto step = [&](auto odd_c, const int j, uint32_t (&pw)[32], uint32_t (&pr)[32]) {
        constexpr bool ODD = decltype(odd_c)::value;
        const bool first = !ODD && (j & 2) == 0, last = ODD && j == 7;
        const uint32_t ph = (j >> 1) & 1;
        float i0, i1, a0, a1;
        const bool so = !ODD && j == 4;
        if (so) { i0 = inv_quad_sum(l0); i1 = inv_quad_sum(l1); l0 = 0.f; l1 = 0.f; }
        bool redo = !ODD && (j | ps) == 0;
        while (true) {
          if (redo) {
            float m0 = fmaxf(s[0], s[1]), m1 = fmaxf(s[2], s[3]);
#pragma unroll
            for (int i = 1; i < 16; i++) { m0 = fmaxf(m0, fmaxf(s[4 * i], s[4 * i + 1])); m1 = fmaxf(m1, fmaxf(s[4 * i + 2], s[4 * i + 3])); }
            m0 = fmaxf(m0, __shfl_xor_sync(0xffffffffu, m0, 1)); m1 = fmaxf(m1, __shfl_xor_sync(0xffffffffu, m1, 1));
            m0 = fmaxf(m0, __shfl_xor_sync(0xffffffffu, m0, 2)); m1 = fmaxf(m1, __shfl_xor_sync(0xffffffffu, m1, 2));
            m0 *= SCL2; m1 *= SCL2;
            if (!first) {
              m0 = fmaxf(m0, f0); m1 = fmaxf(m1, f1);
              const float c0 = ex2(f0 - m0), c1 = ex2(f1 - m1);
              l0 *= c0; l1 *= c1;
              wg_wait<0>();
              keep(o);
#pragma unroll
              for (int i = 0; i < 16; i++) { o[4 * i] *= c0; o[4 * i + 1] *= c0; o[4 * i + 2] *= c1; o[4 * i + 3] *= c1; }
            }
            f0 = m0; f1 = m1;
          }
          float b0 = 0.f, b1 = 0.f;
          a0 = 0.f; a1 = 0.f;
#pragma unroll
          for (int i = 0; i < 16; i++) {
            const float e0 = ex2(fmaf(s[4 * i], SCL2, -f0)), e1 = ex2(fmaf(s[4 * i + 1], SCL2, -f0));
            const float e2 = ex2(fmaf(s[4 * i + 2], SCL2, -f1)), e3 = ex2(fmaf(s[4 * i + 3], SCL2, -f1));
            a0 += e0; b0 += e1; a1 += e2; b1 += e3;
            pw[2 * i] = pack_bf(e0, e1); pw[2 * i + 1] = pack_bf(e2, e3);
            if (i == VREL) {
#pragma unroll
              for (int k = 0; k < 2 * VREL + 2; k++) asm volatile("" : "+r"(pw[k])::"memory");
              mbar_wait(bar_mod, 0);
              wg_wait<0>();
              mbar_arrive_cl(rempty, ODD ? 16 : 0, !redo && (ODD || j));
#pragma unroll
              for (int k = 4 * VREL + 4; k < 64; k++) asm volatile("" : "+f"(s[k])::"memory");
            }
          }
          a0 += b0; a1 += b1;
          if (redo) break;
          redo = __any_sync(0xffffffffu, !(a0 + a1 < 0x1p90f) || (!ODD && fminf(a0, a1) < (first ? 0x1p-90f : 0.f)));
          if (!redo) break;
        }
        l0 += a0; l1 += a1;
        keep(pw);
        keep(o);
        if (so) store_chunk<0>(o, i0, i1, qw + unit_of(qt, 0) + frag_offset(warp));
        keep(o);
        if (j == (ODD ? 5 : 0)) { fence_async_smem(); if (ODD) mbar_arrive(bar_ofull + wg * 8); }
        mbar_wait(bfull + (ODD ? 24 : 8), ph);
        bar_sync(2 + wg, 256);
        if (!last) {
          const uint32_t qn = qt >> (j >= 3 ? 8 : 0);
          wg_fence();
          issue_qk(s, qw + unit_of(qn, 0), qw + unit_of(qn, 1), base + unit_of(at, ODD ? 3 : 1));
          wg_commit();
          mbar_wait(bfull + (ODD ? 0 : 16), ODD ? ph ^ 1 : ph);
        }
        if (so) { store_chunk<1>(o, i0, i1, qw + unit_of(qt, 1) + frag_offset(warp)); keep(o); }
        wg_fence();
        issue_pv(o, pw, base + unit_of(at, ODD ? (last ? 3 : 0) : 2), !first);
        wg_commit();
        bar_arrive(3 - wg, 256);
        wg_wait<1>();
        keep(s);
        mbar_arrive_cl(rempty, ODD ? 24 : 8, !last);
        PROF(4, tid == 0 && ps == 1, 51 + j);
      };
      uint32_t pa[32], pb[32];
#pragma unroll 1
      for (int j = 0; j < 8; j += 2) {
        step(std::false_type{}, j, pa, pb);
        step(std::true_type{}, j + 1, pb, pa);
      }
      {
        const float i0 = inv_quad_sum(l0), i1 = inv_quad_sum(l1);
        wg_wait<0>();
        keep(o);
        mbar_arrive_cl(rempty, 24);
        store_chunk<0>(o, i0, i1, qw + unit_of(qt, 2) + frag_offset(warp));
        store_chunk<1>(o, i0, i1, qw + unit_of(qt, 3) + frag_offset(warp));
        fence_async_smem();
        mbar_arrive(bar_ofull + 16 + wg * 8);
      }
      PROF(2, tid == 0, 10 + ps * 8);
    }

    const int ln = fresh_lane(), g = ln >> 2, tq = ln & 3, ct = warp * 32 + ln;
    const bool lane0 = ln == 0;
    const int lrow0 = warp * 16 + g;
    const int grow0 = rb * 128 + lrow0;
    const uint32_t res = base + OFF_RES, trow = res + wg * 8192 + frag_offset(warp);
    uint32_t xr[32];
    uint4 sv[4], own;
    uint32_t* sp[4];
#pragma unroll
    for (int k = 0; k < 4; k++) sp[k] = g_stats + ((((tq >> 1) * 4 + k) ^ cj) * SEQ + grow0 + (tq & 1) * 8) * 4;
    {
      const uint64_t da = make_desc(base + wg * 8192, 16, 1024), db = make_desc(base, 8192, 1024);
      constexpr int U = UNIT / 16;
#define HALF_STAGE(acc, xu, wu) _Pragma("unroll") for (int kk = 0; kk < 4; kk++) mma_ss<1>(acc, da + (xu) * U + kk * 2, db + (wu) * U + kk * 128, 1)
      PROF(10, ct == PT, 19); STAMP(0);
      cluster_arrive();
      mbar_wait(gfull, 1);
      mbar_wait(gfull + 8, 1);
      bar_sync(2 + wg, 256);
      wg_fence();
      HALF_STAGE(o, 7, 1);
      HALF_STAGE(o, 8, 3);
      wg_commit();
      STAMP(16);
      mbar_wait(gfull + 16, 1);
      STAMP(17);
      wg_fence();
      HALF_STAGE(o, 6, 11);
      wg_commit();
      bar_arrive(3 - wg, 256);
      mbar_wait(bar_par, 0);
      uint32_t* xo = g_xch + ((size_t)b * 8 * 256 + ct) * 4;
      const uint32_t* xi = g_xch + ((size_t)(b ^ 2) * 8 * 256 + ct) * 4;
      const uint32_t par1 = (~lds1(par + PAR_CONST + 4) & 1) << 16;
      wg_wait<1>();
      mbar_arrive_pred(bar_rel, lane0);
      wg_wait<0>();
      keep(o);
      mbar_arrive_pred(bar_ring, lane0);
      PROF(8, ct == PT, 20); STAMP(1);
#define SEND(i) st_b128(xo + (i) * 1024, (pack_bf(o[8 * (i)], o[8 * (i) + 1]) & ~0x10000u) | par1, pack_bf(o[8 * (i) + 2], o[8 * (i) + 3]), \
                        pack_bf(o[8 * (i) + 4], o[8 * (i) + 5]), pack_bf(o[8 * (i) + 6], o[8 * (i) + 7]))
#pragma unroll
      for (int i = 0; i < NS1; i++) SEND(i);
      PROF(8, ct == PT, 21); STAMP(2);
      bar_sync(2 + wg, 256);
      wg_fence();
      HALF_STAGE(s, 7, 0);
      HALF_STAGE(s, 8, 2);
      HALF_STAGE(s, 6, 10);
      wg_commit();
      bar_arrive(3 - wg, 256);
      STAMP(18);
      mbar_wait(gfull + 24, 1);
#pragma unroll
      for (int i = NS1; i < 8; i++) SEND(i);
      uint4 v[8];
      STAMP(19);
      mbar_wait(bar_xres, 0);
      wg_wait<0>();
      mbar_arrive_pred(bar_ring + 8, lane0);
      bar_sync(2 + wg, 256);
      STAMP(20);
#pragma unroll
      for (int i = 0; i < LD2; i++) v[i] = ld_b128(xi + i * 1024);
      mbar_wait(bar_xres, 0);
      wg_fence();
      HALF_STAGE(s, 9, 4);
      wg_commit();
      mbar_wait(bar_rx, 0);
      wg_fence();
      HALF_STAGE(s, 1, 5);
      wg_commit();
      bar_arrive(3 - wg, 256);
      STAMP(21);
#pragma unroll
      for (int i = LD2; i < 8; i++) v[i] = ld_b128(xi + i * 1024);
      mbar_wait(bar_xres, 0);
      wg_wait<0>();
      keep(s);
      mbar_arrive_pred(bar_ring + 16, lane0);
      PROF(10, ct == PT, 23); STAMP(4);
#pragma unroll
      for (int i = 0; i < 16; i += 2) ldmatrix4((trow ^ ((i & 7) << 4)) + (i >> 3) * 16384, xr[2 * i], xr[2 * i + 1], xr[2 * i + 2], xr[2 * i + 3]);
      uint32_t ga[16];
      uint4 bw[8];
#pragma unroll
      for (int i = 0; i < 8; i++) {
        if (!(i & 1)) {
          const uint4 t = lds4(par + PAR_SINK + i * 32 + tq * 16);
          ga[2 * i] = t.x; ga[2 * i + 1] = t.y; ga[2 * i + 2] = t.z; ga[2 * i + 3] = t.w;
        }
        bw[i] = lds4(par + PAR_T1 + i * 64 + tq * 16);
        if (!(g & 1)) { bw[i].x = 0x3f803f80u; bw[i].y = 0x3f803f80u; }
      }
      uint32_t pk[32];
      pack_p(s, pk);
      keep(pk);
      {
        uint32_t n = 0, miss;
        do {
          miss = 0;
#pragma unroll
          for (int i = 0; i < 8; i++) miss |= v[i].x ^ par1;
          miss = __any_sync(0xffffffffu, miss & 0x10000u);
          if (miss) {
#pragma unroll
            for (int i = 0; i < 8; i++)
              asm volatile("{ .reg .pred p; .reg .b32 t; xor.b32 t, %0, %5; and.b32 t, t, 0x10000; setp.ne.u32 p, t, 0;\n"
                           "@p ld.relaxed.gpu.global.v4.u32 {%0, %1, %2, %3}, [%4]; }"
                           : "+r"(v[i].x), "+r"(v[i].y), "+r"(v[i].z), "+r"(v[i].w) : "l"(xi + i * 1024), "r"(par1) : "memory");
          }
          watchdog(n);
        } while (miss);
      }
      PROF(8, ct == PT, 22); STAMP(3);
      float ds[4] = {0.f, 0.f, 0.f, 0.f}, dl[4] = {0.f, 0.f, 0.f, 0.f}, q0[4] = {0.f, 0.f, 0.f, 0.f}, q1[4] = {0.f, 0.f, 0.f, 0.f};
#pragma unroll
      for (int i = 0; i < 8; i++) {
        const uint32_t u0 = hfma2(ga[2 * i], hadd2(pk[4 * i], v[i].x & ~0x10000u), xr[4 * i]);
        const uint32_t u1 = hfma2(ga[2 * i], hadd2(pk[4 * i + 1], v[i].y), xr[4 * i + 1]);
        const uint32_t u2 = hfma2(ga[2 * i + 1], hadd2(pk[4 * i + 2], v[i].z), xr[4 * i + 2]);
        const uint32_t u3 = hfma2(ga[2 * i + 1], hadd2(pk[4 * i + 3], v[i].w), xr[4 * i + 3]);
        xr[4 * i] = u0; xr[4 * i + 1] = u1; xr[4 * i + 2] = u2; xr[4 * i + 3] = u3;
        mma16816(ds, u0, u1, u2, u3, bw[i].x, bw[i].y);
        mma16816(dl, u0, u1, u2, u3, bw[i].z, bw[i].w);
        mma16816(q0, u0, u1, u2, u3, u0, u2);
        mma16816(q1, u0, u1, u2, u3, u1, u3);
      }
      const float sqa = __shfl_sync(0xffffffffu, (g & 1) ? q0[1] : q0[0], g * 4 + (g >> 1));
      const float sqb = __shfl_sync(0xffffffffu, (g & 1) ? q1[3] : q1[2], g * 4 + (g >> 1));
      own = (tq & 1) ? make_uint4(__float_as_uint(ds[2]), __float_as_uint(sqb), __float_as_uint(ds[3] + dl[3]), tag)
                                 : make_uint4(__float_as_uint(ds[0]), __float_as_uint(sqa), __float_as_uint(ds[1] + dl[1]), tag);
      if (tq < 2) st_b128(sp[0], own.x, own.y, own.z, own.w);
#pragma unroll
      for (int k = 0; k < 4; k++) sv[k] = make_uint4(0, 0, 0, 0);
    }
    PROF(8, ct == PT, 29); STAMP(5);
    uint32_t mm, ih, il;
    float rbest;
    uint32_t wf[128];
    const uint32_t frow = (ln & 7) + (ln >> 4) * 8;
    const uint32_t wfo = base + (warp & 1) * 8192 + frow * 64 + ((((ln >> 3) & 1) ^ ((frow >> 1) & 3)) << 4);
#define LOAD_WF(m) _Pragma("unroll") for (int f = 0; f < 16; f++) {                                                   \
      const int r = ((f >> 1) * 4 + (m) * 2 + (f & 1)) * 4;                                                           \
      ldmatrix4t(((wfo + unit_of((m) ? FT_U : FT_G, warp >> 1)) ^ ((f & 1) * 32)) + (f >> 1) * 1024, wf[r], wf[r + 1], wf[r + 2], wf[r + 3]); \
    }
    bool early;
    {
#pragma unroll
      for (int i = 0; i < 16; i += 2) stmatrix4((trow ^ ((i & 7) << 4)) + (i >> 3) * 16384, xr[2 * i], xr[2 * i + 1], xr[2 * i + 2], xr[2 * i + 3]);
      const uint4 cst = lds4(par + PAR_CONST);
      const float A1 = __uint_as_float(cst.x), A2 = __uint_as_float(cst.z);
      uint32_t n = 0;
      early = false;
#pragma unroll 1
      while (true) {
        uint32_t miss;
        asm volatile("{ .reg .pred p0, p1, p2, p3; .reg .b64 u, v; .reg .b128 w;\n"
                     "setp.ge.u32 p0, %22, 2; setp.ne.and.u32 p0, %4, %21, p0; setp.ne.u32 p1, %8, %21; setp.ne.u32 p2, %12, %21; setp.ne.u32 p3, %16, %21;\n"
                     "@p0 ld.relaxed.gpu.global.v4.u32 {%1, %2, %3, %4}, [%17];\n"
                     "@p1 ld.relaxed.gpu.global.v4.u32 {%5, %6, %7, %8}, [%18];\n"
                     "@p2 ld.relaxed.gpu.global.v4.u32 {%9, %10, %11, %12}, [%19];\n"
                     "@p3 ld.relaxed.gpu.global.v4.u32 {%13, %14, %15, %16}, [%20];\n"
                     "or.pred p0, p0, p1; or.pred p2, p2, p3; or.pred p0, p0, p2; vote.sync.any.pred p0, p0, 0xffffffff; selp.u32 %0, 1, 0, p0; }"
                     : "=r"(miss), "+r"(sv[0].x), "+r"(sv[0].y), "+r"(sv[0].z), "+r"(sv[0].w), "+r"(sv[1].x), "+r"(sv[1].y), "+r"(sv[1].z), "+r"(sv[1].w),
                       "+r"(sv[2].x), "+r"(sv[2].y), "+r"(sv[2].z), "+r"(sv[2].w), "+r"(sv[3].x), "+r"(sv[3].y), "+r"(sv[3].z), "+r"(sv[3].w)
                     : "l"(sp[0]), "l"(sp[1]), "l"(sp[2]), "l"(sp[3]), "r"(tag), "r"(tq) : "memory");
        if (!miss) break;
        if (!early && (b >= NFFN || __all_sync(0xffffffffu, mbar_test(bar_box + (warp >> 1) * 8, 0)))) {
          early = true;
          LOAD_WF(0);
          __syncwarp();
          mbar_arrive_pred(bar_gate, lane0);
        }
        watchdog(n);
      }
      const uint4 v0 = tq < 2 ? own : sv[0], v1 = sv[1], v2 = sv[2], v3 = sv[3];
      PROF(8, ct == PT, 30); STAMP(6);
      float su = (__uint_as_float(v0.x) + __uint_as_float(v1.x)) + (__uint_as_float(v2.x) + __uint_as_float(v3.x));
      float sq = (__uint_as_float(v0.y) + __uint_as_float(v1.y)) + (__uint_as_float(v2.y) + __uint_as_float(v3.y));
      float dt = (__uint_as_float(v0.z) + __uint_as_float(v1.z)) + (__uint_as_float(v2.z) + __uint_as_float(v3.z));
      su += __shfl_xor_sync(0xffffffffu, su, 2); sq += __shfl_xor_sync(0xffffffffu, sq, 2); dt += __shfl_xor_sync(0xffffffffu, dt, 2);
      const float m = su * (1.f / DM);
      float mb, sd;
      ln_scalars(m, fmaxf(sq * (1.f / DM) - m * m, 0.f), mb, sd);
      const float inv = rcp(sd);
      rbest = (dt - mb * A1) * inv + A2;
      mm = pack_bf(mb, mb);
      ih = pack_bf(inv, inv);
      const float lo = inv - bf_lo(ih);
      il = pack_bf(lo, lo);
    }
    int ibest;
    {
      const uint32_t bits = __float_as_uint(rbest);
      const uint32_t key = (((int)bits < 0 ? ~bits : bits | 0x80000000u) & ~0x1ffu) | ((127 - lrow0 - (tq & 1) * 8) << 2) | tag;
      sts1(par + PAR_RED + warp * 4, __reduce_max_sync(0xffffffffu, key));
      PROF(8, ct == PT, 38); STAMP(7);
      bar_sync(1, 256);
      const uint4 ka = lds4(par + PAR_RED), kb = lds4(par + PAR_RED + 16);
      const uint32_t k2 = max(max(max(ka.x, ka.y), max(ka.z, ka.w)), max(max(kb.x, kb.y), max(kb.z, kb.w)));
      if (ct < CR && cj == 0) st_relaxed(g_cand + ct * 512 + rb * CS, k2);
      ibest = 127 - ((k2 >> 2) & 127);
    }
    PROF(8, ct == PT, 39); STAMP(8);
    if ((ibest >> 4) == warp) {
      const int src = (ibest & 7) * 4 + ((ibest >> 3) & 1), ch = g * 2;
      const uint32_t cm = __shfl_sync(0xffffffffu, mm, src), ch_ = __shfl_sync(0xffffffffu, ih, src), cl = __shfl_sync(0xffffffffu, il, src);
      const uint32_t xa = res + (ch >> 3) * 16384 + ibest * 128 + (((ch & 7) ^ (ibest & 7)) << 4) + tq * 4;
      const uint32_t x0 = lds1(xa), x1 = lds1(xa ^ 16);
      const uint2 p0 = lds2(par + PAR_T2 + ch * 64 + tq * 16), p1 = lds2(par + PAR_T2 + ch * 64 + 64 + tq * 16);
      uint32_t* dst = g_row + rb * 2 * DM + cj * 128 + ln * 4;
      st_pairs(dst, ln_mod(x0, cm, ch_, cl, p0.x, p0.y), ln_mod(x1, cm, ch_, cl, p1.x, p1.y), tag);
      st_pairs(dst + DM, x0, x1, tag);
      __syncwarp();
    }
    PROF(8, ct == PT, 37); STAMP(9);
    uint32_t wd[64];
    const uint32_t wda = base + unit_of(FT_D, warp >> 1) + (warp & 1) * 8192 + frow * 128 + ((((ln >> 3) & 1) ^ (ln & 7)) << 4);
#define LOAD_WD(f) ldmatrix4t((wda ^ ((((f) >> 1) & 3) * 32)) + ((f) >> 3) * 4096 + ((f) & 1) * 2048, wd[4 * (f)], wd[4 * (f) + 1], wd[4 * (f) + 2], wd[4 * (f) + 3])
    if (!early) {
      if (b < NFFN) mbar_wait(bar_box + (warp >> 1) * 8, 0);
      LOAD_WF(0);
      __syncwarp();
      mbar_arrive_pred(bar_gate, lane0);
    }
    if (b < NFFN) {
      const uint32_t own = base + unit_of(FT_G, warp >> 1) + (warp & 1) * 8192;
      mbar_wait(bar_box + (4 + (warp >> 1)) * 8, 0);
      LOAD_WF(1);
      uint32_t* const ydst = ypart_slot(b, warp * 16 + (tq & 1) * 8 + g);
      PROF(8, ct == PT, 31); STAMP(10);
      bool wdok;
      {
        uint32_t n = 0;
        while (!(wdok = __all_sync(0xffffffffu, mbar_test(bar_box + (8 + (warp >> 1)) * 8, 0))) && !__all_sync(0xffffffffu, mbar_test(bar_sel, 0))) watchdog(n);
      }
      if (wdok) {
#pragma unroll
        for (int f = 0; f < 16; f++) LOAD_WD(f);
      }
      STAMP(11);
      mbar_wait(bar_sel, 0);
      PROF(8, ct == PT, 33); STAMP(12);
      float d[8][4];
#pragma unroll
      for (int i = 0; i < 4; i++) { d[i][0] = 0.f; d[i][1] = 0.f; d[i][2] = 0.f; d[i][3] = 0.f; }
#pragma unroll
      for (int ks = 0; ks < 8; ks++) {
        const uint2 hb = lds2(own + 256 + ks * 32 + tq * 8);
#pragma unroll
        for (int mt = 0; mt < 4; mt++) {
          const int r = ks * 16 + mt * 4;
          mma16816(d[mt], wf[r], wf[r + 1], wf[r + 2], wf[r + 3], hb.x, hb.y);
        }
      }
      sts2(own + (tq * 8 + g) * 8, __float_as_uint((tq & 2) ? ((tq & 1) ? d[1][2] : d[1][0]) : ((tq & 1) ? d[0][2] : d[0][0])),
           __float_as_uint((tq & 2) ? ((tq & 1) ? d[3][2] : d[3][0]) : ((tq & 1) ? d[2][2] : d[2][0])));
      bar_sync(1, 256);
      uint32_t ab[4];
      {
        float G = 0.f, U = 0.f;
        uint2 pv[8];
#pragma unroll
        for (int w8 = 0; w8 < 8; w8++) pv[w8] = lds2(base + ln * 8 + ((FT_G >> (w8 >> 1) * 4) & 15) * UNIT + (w8 & 1) * 8192);
#pragma unroll
        for (int w8 = 0; w8 < 8; w8 += 2) {
          G += __uint_as_float(pv[w8].x) + __uint_as_float(pv[w8 + 1].x);
          U += __uint_as_float(pv[w8].y) + __uint_as_float(pv[w8 + 1].y);
        }
        const float act = rbf(silu_f(rbf(G))) * rbf(U);
        const uint32_t pk = pack_bf(act, __shfl_down_sync(0xffffffffu, act, 1));
#pragma unroll
        for (int i = 0; i < 4; i++) ab[i] = __shfl_sync(0xffffffffu, pk, i * 8 + tq * 2);
      }
      if (!wdok) {
        mbar_wait(bar_box + (8 + (warp >> 1)) * 8, 0);
#pragma unroll
        for (int f = 0; f < 16; f++) LOAD_WD(f);
      }
      PROF(8, ct == PT, 34); STAMP(13);
#pragma unroll
      for (int mt = 0; mt < 8; mt++) {
        d[mt][0] = 0.f; d[mt][1] = 0.f; d[mt][2] = 0.f; d[mt][3] = 0.f;
        mma16816(d[mt], wd[mt * 8], wd[mt * 8 + 1], wd[mt * 8 + 2], wd[mt * 8 + 3], ab[0], ab[1]);
        mma16816(d[mt], wd[mt * 8 + 4], wd[mt * 8 + 5], wd[mt * 8 + 6], wd[mt * 8 + 7], ab[2], ab[3]);
      }
      uint32_t yw[4];
#pragma unroll
      for (int i = 0; i < 4; i++) yw[i] = (tq & 1) ? pack_bf(d[2 * i][2], d[2 * i + 1][2]) : pack_bf(d[2 * i][0], d[2 * i + 1][0]);
      if (tq < 2) st_b128(ydst, (yw[0] & ~1u) | (tag & 1), (yw[1] & ~1u) | (tag >> 1), yw[2], yw[3]);
      PROF(8, ct == PT, 35); STAMP(14);
    }
    mbar_wait(bar_sel, 0);
    mbar_arrive_pred(bar_win, ct == 0);
    const int iwin = lds1(par + PAR_CONST + 60) & 0x7ff;
    const bool cand = (iwin >> 4) == rb * 8 + warp;
    {
      const uint32_t mm0 = __shfl_sync(0xffffffffu, mm, ln & ~1), mm1 = __shfl_sync(0xffffffffu, mm, ln | 1);
      const uint32_t ih0 = __shfl_sync(0xffffffffu, ih, ln & ~1), ih1 = __shfl_sync(0xffffffffu, ih, ln | 1);
      const uint32_t il0 = __shfl_sync(0xffffffffu, il, ln & ~1), il1 = __shfl_sync(0xffffffffu, il, ln | 1);
#pragma unroll 1
      for (int hf = 0; hf < 2; hf++) {
        uint32_t x[16];
#pragma unroll
        for (int i = 0; i < 8; i += 2) ldmatrix4((trow ^ (i << 4)) + hf * 16384, x[2 * i], x[2 * i + 1], x[2 * i + 2], x[2 * i + 3]);
#pragma unroll
        for (int i = 0; i < 8; i++) {
          const uint4 pv = lds4(par + PAR_T2 + (hf * 8 + i) * 64 + tq * 16);
          x[2 * i] = hfma2(hfma2(ln_norm(x[2 * i], mm0, ih0, il0), pv.x, pv.y), pv.z, x[2 * i]);
          x[2 * i + 1] = hfma2(hfma2(ln_norm(x[2 * i + 1], mm1, ih1, il1), pv.x, pv.y), pv.z, x[2 * i + 1]);
        }
#pragma unroll
        for (int i = 0; i < 8; i += 2) stmatrix4((trow ^ (i << 4)) + hf * 16384, x[2 * i], x[2 * i + 1], x[2 * i + 2], x[2 * i + 3]);
        if (!cand) fence_async_smem();
        __syncwarp();
        if (!cand && elect_one()) {
          tma2d_store(&maps.out, res + hf * 16384 + warp * 2048, cj * 128 + hf * 64, rb * 128 + warp * 16);
          asm volatile("cp.async.bulk.commit_group;" ::: "memory");
        }
      }
    }
    if (cand) {
      const int wrow0 = warp * 16;
#pragma unroll 2
      for (int p = 0; p < 8; p++) {
        const int row = 2 * p + (ln >> 4), ch = ln & 15;
        const uint4 v = lds4(res + (ch >> 3) * 16384 + (wrow0 + row) * 128 + (((ch & 7) ^ (row & 7)) << 4));
        if (rb * 128 + wrow0 + row != iwin) *reinterpret_cast<uint4*>(P.out + (size_t)(rb * 128 + wrow0 + row) * DM + cj * 128 + ch * 8) = v;
      }
    }
    asm volatile("cp.async.bulk.wait_group.read 0;" ::: "memory");
    PROF(8, ct == PT, 11); STAMP(15);
    cluster_wait();
  }
}

typedef CUresult (*EncodeFn)(CUtensorMap*, CUtensorMapDataType, cuuint32_t, void*, const cuuint64_t*, const cuuint64_t*,
                             const cuuint32_t*, const cuuint32_t*, CUtensorMapInterleave, CUtensorMapSwizzle,
                             CUtensorMapL2promotion, CUtensorMapFloatOOBfill);

void map2d(EncodeFn enc, CUtensorMap* m, const void* p, uint64_t rows, uint64_t cols, uint32_t brows) {
  cuuint64_t dims[2] = {cols, rows}, strides[1] = {cols * 2};
  cuuint32_t box[2] = {64, brows}, es[2] = {1, 1};
  enc(m, CU_TENSOR_MAP_DATA_TYPE_BFLOAT16, 2, const_cast<void*>(p), dims, strides, box, es, CU_TENSOR_MAP_INTERLEAVE_NONE,
      CU_TENSOR_MAP_SWIZZLE_128B, CU_TENSOR_MAP_L2_PROMOTION_L2_256B, CU_TENSOR_MAP_FLOAT_OOB_FILL_NONE);
}
void map2d_narrow(EncodeFn enc, CUtensorMap* m, const void* p, uint64_t rows, uint64_t cols, uint32_t brows) {
  cuuint64_t dims[2] = {cols, rows}, strides[1] = {cols * 2};
  cuuint32_t box[2] = {32, brows}, es[2] = {1, 1};
  enc(m, CU_TENSOR_MAP_DATA_TYPE_BFLOAT16, 2, const_cast<void*>(p), dims, strides, box, es, CU_TENSOR_MAP_INTERLEAVE_NONE,
      CU_TENSOR_MAP_SWIZZLE_64B, CU_TENSOR_MAP_L2_PROMOTION_L2_64B, CU_TENSOR_MAP_FLOAT_OOB_FILL_NONE);
}
void map3d(EncodeFn enc, CUtensorMap* m, const void* p, uint64_t rows, uint64_t cols, uint32_t brows, uint32_t nch) {
  cuuint64_t dims[3] = {64, rows, cols / 64}, strides[2] = {cols * 2, 128};
  cuuint32_t box[3] = {64, brows, nch}, es[3] = {1, 1, 1};
  enc(m, CU_TENSOR_MAP_DATA_TYPE_BFLOAT16, 3, const_cast<void*>(p), dims, strides, box, es, CU_TENSOR_MAP_INTERLEAVE_NONE,
      CU_TENSOR_MAP_SWIZZLE_128B, CU_TENSOR_MAP_L2_PROMOTION_L2_256B, CU_TENSOR_MAP_FLOAT_OOB_FILL_NONE);
}

}

extern "C" void kernel_launch(void* const* d_in, const int* in_sizes, int n_in, void* d_out, int out_size) {
  (void)in_sizes; (void)n_in; (void)out_size;
  static EncodeFn enc = nullptr;
  if (!enc) {
    void* fn = nullptr;
    cudaDriverEntryPointQueryResult st;
    cudaGetDriverEntryPoint("cuTensorMapEncodeTiled", &fn, cudaEnableDefault, &st);
    enc = (EncodeFn)fn;
    cudaFuncSetAttribute(fused_kernel, cudaFuncAttributeMaxDynamicSharedMemorySize, SMEM_BYTES);
  }
  Maps maps;
  map2d(enc, &maps.x, d_in[0], SEQ, DM, 128);
  map2d(enc, &maps.out, d_out, SEQ, DM, 16);
  map3d(enc, &maps.wq, d_in[3], DM, NQ, 64, 2);
  map3d(enc, &maps.k, d_in[1], 4 * SK, 128, 128, 1);
  map3d(enc, &maps.v, d_in[2], 4 * SK, 128, 128, 1);
  map3d(enc, &maps.wo, d_in[4], NQ, DM, 64, 2);
  map2d_narrow(enc, &maps.wg, d_in[7], DM, FF, 256);
  map2d_narrow(enc, &maps.wu, d_in[8], DM, FF, 256);
  map3d(enc, &maps.wd, d_in[9], FF, DM, 32, 4);
  map2d_narrow(enc, &maps.wm, d_in[11], DM, NMOD, 256);
  Ptrs p;
  p.x = (const __nv_bfloat16*)d_in[0];
  p.w_r = (const __nv_bfloat16*)d_in[6];
  p.w_gate = (const __nv_bfloat16*)d_in[7];
  p.w_up = (const __nv_bfloat16*)d_in[8];
  p.w_down = (const __nv_bfloat16*)d_in[9];
  p.c = (const __nv_bfloat16*)d_in[10];
  p.w_mod = (const __nv_bfloat16*)d_in[11];
  p.out = (__nv_bfloat16*)d_out;
  fused_kernel<<<NMAIN + NHELP, 384, SMEM_BYTES>>>(maps, p);
}
```

```cpp
#include <cuda_runtime.h>
#include <cuda_bf16.h>
#include <cuda.h>
#include <stdint.h>
#include <type_traits>

#define HD 2
#define HDX 2
#define NRS 8
#define OSL 900
#define OSL2 400
#define RSL 40
#define VREL 5
#define OPS 8192
#define ODS1 5
#define ODS 7
#define PG0 15
#define WB 2
#define WN 20
#define HU 32
#define RES0 17
#define RES1 20
#define GOST 20
#define NS1 5
#define LD2 4
#define FPACE0 2
#define FPACE 3
#define CR 8
#define CS 8

namespace {

constexpr int SEQ = 2048, DM = 1024, NQ = 4096, SK = 2048, WIN = 512, FF = 3584, NMOD = 6144;
constexpr int NMAIN = 128, NHELP = 4, NFFN = 112;
constexpr int NSLOT = 4, SLOT_BYTES = 32768, UNIT = 16384, GST_BYTES = 3 * UNIT;
constexpr uint32_t XT1 = 0xDCBA, XT2 = 0x9687;
constexpr uint32_t WT0 = 0xA741, WT1 = 0x7420, WT2 = 0x4A20;
constexpr uint32_t AT0 = WT1, AT1 = WT2;
constexpr uint32_t QT = 0xDC9696DC;
constexpr int OFF_STAGE = 12 * UNIT;
constexpr uint32_t FT_G = 0x07B3, FT_U = 0xA628, FT_D = 0x5149;
constexpr int OFF_RES = 12 * UNIT;
constexpr int OFF_PAR = 14 * UNIT;
constexpr int OFF_BAR = OFF_PAR + 2528;
constexpr int SMEM_BYTES = OFF_BAR + 544;
static_assert(SMEM_BYTES <= 232448, "smem");

constexpr int PAR_T1 = 0;
constexpr int PAR_T2 = 512;
constexpr int PAR_CONST = 1536;
constexpr int PAR_RED = 1600;
constexpr int PAR_SINK = 2176;

struct Maps {
  CUtensorMap x, wq, k, v, wo, wg, wu, wd, wm, out;
};
struct Ptrs {
  const __nv_bfloat16 *x, *w_r, *c, *w_mod, *w_gate, *w_up, *w_down;
  __nv_bfloat16* out;
};

__device__ __align__(1024) uint8_t g_act[16 * 80 * UNIT];
__device__ __align__(128) uint32_t g_mod[NMOD];
__device__ __align__(128) uint32_t g_modp[2 * 2 * DM];
__device__ __align__(128) uint32_t g_ln1[SEQ * 4];
__device__ __align__(128) uint32_t g_cnt_h[16 * 32];
__device__ __align__(128) uint32_t g_cnt_o[128 * 32];
__device__ __align__(128) uint32_t g_xch[NMAIN * 8 * 256 * 4];
__device__ __align__(128) uint32_t g_stats[8 * SEQ * 4];
__device__ __align__(128) uint32_t g_cand[CR * 512];
__device__ __align__(128) uint32_t g_row[16 * 2 * DM];
__device__ __align__(128) uint32_t g_ypart[NMAIN * NFFN * 4];
__device__ __forceinline__ uint32_t* ypart_slot(int writer, int reader) { return g_ypart + (writer * NMAIN + reader) * 4; }
__device__ uint32_t g_epoch;

__device__ __forceinline__ uint32_t fresh_lane() { uint32_t l; asm volatile("mov.u32 %0, %%laneid;" : "=r"(l)); return l; }
__device__ __forceinline__ uint32_t frag_offset(int warp) {
  const uint32_t l = fresh_lane();
  return ((warp & 3) * 16 + (l & 15)) * 128 + (((l >> 4) ^ (l & 7)) << 4);
}
__device__ __forceinline__ bool elect_one() {
  uint32_t p;
  asm volatile("{ .reg .pred q; elect.sync _|q, 0xffffffff; selp.u32 %0, 1, 0, q; }" : "=r"(p));
  return p;
}
__device__ __forceinline__ uint32_t smem_u32(const void* p) { return (uint32_t)__cvta_generic_to_shared(p); }
__device__ __forceinline__ void mbar_init(uint32_t bar, uint32_t cnt) {
  asm volatile("mbarrier.init.shared::cta.b64 [%0], %1;" ::"r"(bar), "r"(cnt) : "memory");
}
__device__ __forceinline__ void mbar_expect_tx(uint32_t bar, uint32_t bytes) {
  asm volatile("mbarrier.arrive.expect_tx.shared::cta.b64 _, [%0], %1;" ::"r"(bar), "r"(bytes) : "memory");
}
__device__ __forceinline__ void mbar_arrive(uint32_t bar) {
  asm volatile("mbarrier.arrive.shared::cta.b64 _, [%0];" ::"r"(bar) : "memory");
}
__device__ __forceinline__ void mbar_arrive_pred(uint32_t bar, bool p) {
  asm volatile("{ .reg .pred p; setp.ne.b32 p, %1, 0; @p mbarrier.arrive.shared::cta.b64 _, [%0]; }" ::"r"(bar), "r"((int)p) : "memory");
}
__device__ __forceinline__ void mbar_arrive_cl(uint32_t bar, uint32_t off, bool p = true) {
  asm volatile("{ .reg .pred p, q; .reg .b32 a; setp.ne.b32 q, %2, 0; setp.ne.and.b32 p, %0, 0, q; add.u32 a, %0, %1; @p mbarrier.arrive.shared::cluster.b64 _, [a]; }"
               ::"r"(bar), "r"(off), "r"((int)p) : "memory");
}
__device__ __forceinline__ uint32_t mapa(uint32_t addr, uint32_t cta) {
  uint32_t r; asm("mapa.shared::cluster.u32 %0, %1, %2;" : "=r"(r) : "r"(addr), "r"(cta)); return r;
}
__device__ __forceinline__ void cluster_arrive() { asm volatile("barrier.cluster.arrive.relaxed.aligned;" ::: "memory"); }
__device__ __forceinline__ void cluster_wait() { asm volatile("barrier.cluster.wait.aligned;" ::: "memory"); }
__device__ __forceinline__ void watchdog(uint32_t& n) {
}
__device__ __forceinline__ void mbar_wait(uint32_t bar, uint32_t parity) {
  asm volatile("{\n.reg .pred p;\nWAIT_%=:\nmbarrier.try_wait.parity.shared::cta.b64 p, [%0], %1;\n@!p bra WAIT_%=;\n}" ::"r"(bar), "r"(parity) : "memory");
}
__device__ __forceinline__ bool mbar_test(uint32_t bar, uint32_t parity) {
  uint32_t ok;
  asm volatile("{\n.reg .pred p;\nmbarrier.test_wait.parity.shared::cta.b64 p, [%1], %2;\nselp.u32 %0, 1, 0, p;\n}" : "=r"(ok) : "r"(bar), "r"(parity) : "memory");
  return ok;
}
__device__ __forceinline__ uint64_t l2_stream() {
  uint64_t f; asm("createpolicy.fractional.L2::evict_first.b64 %0, 1.0;" : "=l"(f)); return f;
}
__device__ __forceinline__ uint64_t l2_normal() {
  uint64_t f; asm("createpolicy.fractional.L2::evict_normal.b64 %0, 1.0;" : "=l"(f)); return f;
}
__device__ __forceinline__ void tma2d(uint32_t dst, const CUtensorMap* m, int c0, int c1, uint32_t bar) {
  asm volatile("cp.async.bulk.tensor.2d.shared::cluster.global.mbarrier::complete_tx::bytes.L2::cache_hint [%0], [%1, {%3, %4}], [%2], %5;"
               ::"r"(dst), "l"(m), "r"(bar), "r"(c0), "r"(c1), "l"(l2_stream()) : "memory");
}
__device__ __forceinline__ void bulk_load(uint32_t dst, const void* src, uint32_t bytes, uint32_t bar) {
  asm volatile("cp.async.bulk.shared::cluster.global.mbarrier::complete_tx::bytes [%0], [%1], %2, [%3];" ::"r"(dst), "l"(src), "r"(bytes), "r"(bar) : "memory");
}
__device__ __forceinline__ void bulk_load_stream(uint32_t dst, const void* src, uint32_t bytes, uint32_t bar, uint64_t pol = l2_stream()) {
  asm volatile("cp.async.bulk.shared::cluster.global.mbarrier::complete_tx::bytes.L2::cache_hint [%0], [%1], %2, [%3], %4;"
               ::"r"(dst), "l"(src), "r"(bytes), "r"(bar), "l"(pol) : "memory");
}
__device__ __forceinline__ void tma2d_store(const CUtensorMap* m, uint32_t src, int c0, int c1) {
  asm volatile("cp.async.bulk.tensor.2d.global.shared::cta.bulk_group [%0, {%2, %3}], [%1];" ::"l"(m), "r"(src), "r"(c0), "r"(c1) : "memory");
}
__device__ __forceinline__ void bulk_store(void* dst, uint32_t src, uint32_t bytes) {
  asm volatile("cp.async.bulk.global.shared::cta.bulk_group [%0], [%1], %2;" ::"l"(dst), "r"(src), "r"(bytes) : "memory");
}
__device__ __forceinline__ int slice_of(int i) { return i + ((i & 7) == 1) - ((i & 7) == 2); }
__device__ __forceinline__ uint32_t unit_of(uint32_t table, uint32_t i) { return ((table >> (i * 4)) & 15) * UNIT; }
__device__ __forceinline__ void tma3d(uint32_t dst, const CUtensorMap* m, int c0, int c1, int c2, uint32_t bar) {
  asm volatile("cp.async.bulk.tensor.3d.shared::cluster.global.mbarrier::complete_tx::bytes.L2::cache_hint [%0], [%1, {%3, %4, %5}], [%2], %6;"
               ::"r"(dst), "l"(m), "r"(bar), "r"(c0), "r"(c1), "r"(c2), "l"(l2_stream()) : "memory");
}
template <bool STREAM>
__device__ __forceinline__ void tma3d_mc(uint32_t dst, const CUtensorMap* m, int c0, int c1, int c2, uint32_t bar) {
  if (STREAM)
    asm volatile("cp.async.bulk.tensor.3d.shared::cluster.global.mbarrier::complete_tx::bytes.multicast::cluster.L2::cache_hint [%0], [%1, {%3, %4, %5}], [%2], %6, %7;"
                 ::"r"(dst), "l"(m), "r"(bar), "r"(c0), "r"(c1), "r"(c2), "h"((uint16_t)3), "l"(l2_stream()) : "memory");
  else
    asm volatile("cp.async.bulk.tensor.3d.shared::cluster.global.mbarrier::complete_tx::bytes.multicast::cluster [%0], [%1, {%3, %4, %5}], [%2], %6;"
                 ::"r"(dst), "l"(m), "r"(bar), "r"(c0), "r"(c1), "r"(c2), "h"((uint16_t)3) : "memory");
}
__device__ __forceinline__ void prefetch_map(const CUtensorMap* m) {
  asm volatile("prefetch.tensormap [%0];" ::"l"(m) : "memory");
}
__device__ __forceinline__ void fence_async() { asm volatile("fence.proxy.async.global;" ::: "memory"); }
__device__ __forceinline__ void fence_async_smem() { asm volatile("fence.proxy.async.shared::cta;" ::: "memory"); }
__device__ __forceinline__ void bar_sync(int id, int n) { asm volatile("bar.sync %0, %1;" ::"r"(id), "r"(n) : "memory"); }
__device__ __forceinline__ void bar_arrive(int id, int n) { asm volatile("bar.arrive %0, %1;" ::"r"(id), "r"(n) : "memory"); }
__device__ __forceinline__ void wg_fence() { asm volatile("wgmma.fence.sync.aligned;" ::: "memory"); }
__device__ __forceinline__ void wg_commit() { asm volatile("wgmma.commit_group.sync.aligned;" ::: "memory"); }
template <int N> __device__ __forceinline__ void wg_wait() { asm volatile("wgmma.wait_group.sync.aligned %0;" ::"n"(N) : "memory"); }
__device__ __forceinline__ uint64_t make_desc(uint32_t addr, uint32_t lbo, uint32_t sbo) {
  return (uint64_t)((addr & 0x3FFFF) >> 4) | ((uint64_t)(lbo >> 4) << 16) | ((uint64_t)(sbo >> 4) << 32) | (1ull << 62);
}
__device__ __forceinline__ uint32_t ld_relaxed(const uint32_t* p) {
  uint32_t v; asm volatile("ld.relaxed.gpu.global.u32 %0, [%1];" : "=r"(v) : "l"(p) : "memory"); return v;
}
__device__ __forceinline__ uint32_t ld_acquire(const uint32_t* p) {
  uint32_t v; asm volatile("ld.acquire.gpu.global.u32 %0, [%1];" : "=r"(v) : "l"(p) : "memory"); return v;
}
__device__ __forceinline__ uint4 ld_relaxed4(const uint32_t* p) {
  uint4 v; asm volatile("ld.relaxed.gpu.global.v4.u32 {%0,%1,%2,%3}, [%4];" : "=r"(v.x), "=r"(v.y), "=r"(v.z), "=r"(v.w) : "l"(p) : "memory"); return v;
}
__device__ __forceinline__ void st_relaxed(uint32_t* p, uint32_t v) {
  asm volatile("st.relaxed.gpu.global.u32 [%0], %1;" ::"l"(p), "r"(v) : "memory");
}
__device__ __forceinline__ void st_relaxed4(uint32_t* p, uint32_t a, uint32_t b, uint32_t c, uint32_t d) {
  asm volatile("st.relaxed.gpu.global.v4.u32 [%0], {%1,%2,%3,%4};" ::"l"(p), "r"(a), "r"(b), "r"(c), "r"(d) : "memory");
}
__device__ __forceinline__ void st_b128(uint32_t* p, uint32_t a, uint32_t b, uint32_t c, uint32_t d) {
  asm volatile("{ .reg .b64 u, v; .reg .b128 w; mov.b64 u, {%1, %2}; mov.b64 v, {%3, %4}; mov.b128 w, {u, v}; st.relaxed.gpu.global.b128 [%0], w; }"
               ::"l"(p), "r"(a), "r"(b), "r"(c), "r"(d) : "memory");
}
__device__ __forceinline__ uint4 ld_b128(const uint32_t* p) {
  uint4 r;
  asm volatile("{ .reg .b64 u, v; .reg .b128 w; ld.relaxed.gpu.global.b128 w, [%4]; mov.b128 {u, v}, w; mov.b64 {%0, %1}, u; mov.b64 {%2, %3}, v; }"
               : "=r"(r.x), "=r"(r.y), "=r"(r.z), "=r"(r.w) : "l"(p) : "memory");
  return r;
}
__device__ __forceinline__ void st_pairs(uint32_t* p, uint32_t a, uint32_t b, uint32_t tag) {
  asm volatile("{ .reg .b64 u, v; mov.b64 u, {%1, %3}; mov.b64 v, {%2, %3}; st.relaxed.gpu.global.v2.b64 [%0], {u, v}; }"
               ::"l"(p), "r"(a), "r"(b), "r"(tag) : "memory");
}
__device__ __forceinline__ uint4 ld_pairs(const uint32_t* p) {
  uint4 v;
  asm volatile("{ .reg .b64 u, v; ld.relaxed.gpu.global.v2.b64 {u, v}, [%4]; mov.b64 {%0, %1}, u; mov.b64 {%2, %3}, v; }"
               : "=r"(v.x), "=r"(v.y), "=r"(v.z), "=r"(v.w) : "l"(p) : "memory");
  return v;
}
__device__ __forceinline__ uint2 ld_pair(const uint32_t* p) {
  uint2 v;
  asm volatile("{ .reg .b64 u; ld.relaxed.gpu.global.b64 u, [%2]; mov.b64 {%0, %1}, u; }" : "=r"(v.x), "=r"(v.y) : "l"(p) : "memory");
  return v;
}
__device__ __forceinline__ void red_release(uint32_t* p, uint32_t v) {
  asm volatile("red.release.gpu.global.add.u32 [%0], %1;" ::"l"(p), "r"(v) : "memory");
}
__device__ __forceinline__ uint32_t ldg_nc1(const void* p) {
  uint32_t v;
  asm volatile("ld.global.nc.u32 %0, [%1];" : "=r"(v) : "l"(p));
  return v;
}
__device__ __forceinline__ uint4 ldg_nc4(const void* p) {
  uint4 v; asm volatile("ld.global.nc.L1::no_allocate.v4.u32 {%0,%1,%2,%3}, [%4];" : "=r"(v.x), "=r"(v.y), "=r"(v.z), "=r"(v.w) : "l"(p)); return v;
}
__device__ __forceinline__ uint4 ldg_stream4(const void* p) {
  uint4 v;
  asm volatile("ld.global.nc.L1::no_allocate.L2::cache_hint.v4.u32 {%0,%1,%2,%3}, [%4], %5;" : "=r"(v.x), "=r"(v.y), "=r"(v.z), "=r"(v.w) : "l"(p), "l"(l2_stream()));
  return v;
}
__device__ __forceinline__ void stg4(void* p, uint4 v) {
  asm volatile("st.global.v4.u32 [%0], {%1,%2,%3,%4};" ::"l"(p), "r"(v.x), "r"(v.y), "r"(v.z), "r"(v.w) : "memory");
}
__device__ __forceinline__ void wait_counter(const uint32_t* p, uint32_t target) {
  uint32_t n = 0;
  while (__any_sync(0xffffffffu, (int)(ld_acquire(p) - target) < 0)) { watchdog(n); }
}
__device__ __forceinline__ uint32_t tagf(float v, uint32_t tag) { return (__float_as_uint(v) & ~3u) | tag; }
__device__ __forceinline__ bool tag_ok(uint4 v, uint32_t tag) { return (((v.x ^ tag) | (v.y ^ tag) | (v.z ^ tag) | (v.w ^ tag)) & 3u) == 0; }
__device__ __forceinline__ float untag_sum(uint32_t a, uint32_t b) { return __uint_as_float(a & ~3u) + __uint_as_float(b & ~3u); }
__device__ __forceinline__ uint4 poll4(const uint32_t* p, uint32_t tag) {
  uint4 v = ld_relaxed4(p);
  uint32_t n = 0;
  while (!__all_sync(0xffffffffu, tag_ok(v, tag))) { v = ld_relaxed4(p); watchdog(n); }
  return v;
}
__device__ __forceinline__ float bf_lo(uint32_t v) { return __uint_as_float(v << 16); }
__device__ __forceinline__ float bf_hi(uint32_t v) { return __uint_as_float(v & 0xffff0000u); }
__device__ __forceinline__ uint32_t pack_bf(float lo, float hi) {
  uint32_t r; asm("cvt.rn.bf16x2.f32 %0, %1, %2;" : "=r"(r) : "f"(hi), "f"(lo)); return r;
}
__device__ __forceinline__ float rbf(float v) { return __uint_as_float(pack_bf(0.f, v) & 0xffff0000u); }
__device__ __forceinline__ uint32_t hmul2(uint32_t a, uint32_t b) {
  uint32_t r; asm("mul.rn.bf16x2 %0, %1, %2;" : "=r"(r) : "r"(a), "r"(b)); return r;
}
__device__ __forceinline__ uint32_t hadd2(uint32_t a, uint32_t b) {
  uint32_t r; asm("add.rn.bf16x2 %0, %1, %2;" : "=r"(r) : "r"(a), "r"(b)); return r;
}
__device__ __forceinline__ uint32_t hsub2(uint32_t a, uint32_t b) {
  uint32_t r; asm("sub.rn.bf16x2 %0, %1, %2;" : "=r"(r) : "r"(a), "r"(b)); return r;
}
__device__ __forceinline__ float rcp(float x) { float r; asm("rcp.approx.ftz.f32 %0, %1;" : "=f"(r) : "f"(x)); return r; }
__device__ __forceinline__ float ex2(float x) { float r; asm("ex2.approx.ftz.f32 %0, %1;" : "=f"(r) : "f"(x)); return r; }
__device__ __forceinline__ void stmatrix4(uint32_t addr, uint32_t a, uint32_t b, uint32_t c, uint32_t d) {
  asm volatile("stmatrix.sync.aligned.m8n8.x4.shared.b16 [%0], {%1,%2,%3,%4};" ::"r"(addr), "r"(a), "r"(b), "r"(c), "r"(d) : "memory");
}
__device__ __forceinline__ void ldmatrix4(uint32_t addr, uint32_t& a, uint32_t& b, uint32_t& c, uint32_t& d) {
  asm volatile("ldmatrix.sync.aligned.m8n8.x4.shared.b16 {%0,%1,%2,%3}, [%4];" : "=r"(a), "=r"(b), "=r"(c), "=r"(d) : "r"(addr) : "memory");
}
__device__ __forceinline__ void ldmatrix4t(uint32_t addr, uint32_t& a, uint32_t& b, uint32_t& c, uint32_t& d) {
  asm volatile("ldmatrix.sync.aligned.m8n8.x4.trans.shared.b16 {%0,%1,%2,%3}, [%4];" : "=r"(a), "=r"(b), "=r"(c), "=r"(d) : "r"(addr) : "memory");
}
__device__ __forceinline__ void mma16816(float (&d)[4], uint32_t a0, uint32_t a1, uint32_t a2, uint32_t a3, uint32_t b0, uint32_t b1) {
  asm volatile("mma.sync.aligned.m16n8k16.row.col.f32.bf16.bf16.f32 {%0,%1,%2,%3}, {%4,%5,%6,%7}, {%8,%9}, {%0,%1,%2,%3};"
               : "+f"(d[0]), "+f"(d[1]), "+f"(d[2]), "+f"(d[3]) : "r"(a0), "r"(a1), "r"(a2), "r"(a3), "r"(b0), "r"(b1));
}
__device__ __forceinline__ void sts1(uint32_t a, uint32_t v) { asm volatile("st.shared.u32 [%0], %1;" ::"r"(a), "r"(v) : "memory"); }
__device__ __forceinline__ uint4 lds4(uint32_t a) {
  uint4 v; asm volatile("ld.shared.v4.u32 {%0,%1,%2,%3}, [%4];" : "=r"(v.x), "=r"(v.y), "=r"(v.z), "=r"(v.w) : "r"(a) : "memory"); return v;
}
__device__ __forceinline__ uint2 lds2(uint32_t a) {
  uint2 v; asm volatile("ld.shared.v2.u32 {%0,%1}, [%2];" : "=r"(v.x), "=r"(v.y) : "r"(a) : "memory"); return v;
}
__device__ __forceinline__ uint32_t lds1(uint32_t a) {
  uint32_t v; asm volatile("ld.shared.u32 %0, [%1];" : "=r"(v) : "r"(a) : "memory"); return v;
}
__device__ __forceinline__ void sts2(uint32_t a, uint32_t x, uint32_t y) { asm volatile("st.shared.v2.u32 [%0], {%1,%2};" ::"r"(a), "r"(x), "r"(y) : "memory"); }
__device__ __forceinline__ void sts4(uint32_t a, uint4 v) {
  asm volatile("st.shared.v4.u32 [%0], {%1,%2,%3,%4};" ::"r"(a), "r"(v.x), "r"(v.y), "r"(v.z), "r"(v.w) : "memory");
}
__device__ __forceinline__ float silu_f(float v) { return __fdividef(v, 1.f + __expf(-v)); }
__device__ __forceinline__ uint32_t hfma2(uint32_t a, uint32_t b, uint32_t c) {
  uint32_t r; asm("fma.rn.bf16x2 %0, %1, %2, %3;" : "=r"(r) : "r"(a), "r"(b), "r"(c)); return r;
}
__device__ __forceinline__ void split_inv(float sd, uint32_t& ih, uint32_t& il) {
  const float inv = rcp(sd);
  ih = pack_bf(inv, inv);
  const float lo = inv - bf_lo(ih);
  il = pack_bf(lo, lo);
}
__device__ __forceinline__ uint32_t ln_norm(uint32_t x, uint32_t mean2, uint32_t ih, uint32_t il) {
  const uint32_t d = hsub2(x, mean2);
  return hfma2(d, ih, hmul2(d, il));
}
__device__ __forceinline__ uint32_t ln_mod(uint32_t x, uint32_t mean2, uint32_t ih, uint32_t il, uint32_t c1, uint32_t sh) {
  return hadd2(hmul2(ln_norm(x, mean2, ih, il), c1), sh);
}

#define R8(a, i) "+f"(a[i]), "+f"(a[i + 1]), "+f"(a[i + 2]), "+f"(a[i + 3]), "+f"(a[i + 4]), "+f"(a[i + 5]), "+f"(a[i + 6]), "+f"(a[i + 7])
#define D64 "{%0,%1,%2,%3,%4,%5,%6,%7,%8,%9,%10,%11,%12,%13,%14,%15,%16,%17,%18,%19,%20,%21,%22,%23,%24,%25,%26,%27,%28,%29,%30,%31," \
            "%32,%33,%34,%35,%36,%37,%38,%39,%40,%41,%42,%43,%44,%45,%46,%47,%48,%49,%50,%51,%52,%53,%54,%55,%56,%57,%58,%59,%60,%61,%62,%63}"
template <int TB>
__device__ __forceinline__ void mma_ss(float (&d)[64], uint64_t da, uint64_t db, int sc) {
  asm volatile("{\n.reg .pred p;\nsetp.ne.b32 p, %66, 0;\n"
               "wgmma.mma_async.sync.aligned.m64n128k16.f32.bf16.bf16 " D64 ", %64, %65, p, 1, 1, 0, %67;\n}"
               : R8(d, 0), R8(d, 8), R8(d, 16), R8(d, 24), R8(d, 32), R8(d, 40), R8(d, 48), R8(d, 56)
               : "l"(da), "l"(db), "r"(sc), "n"(TB));
}
template <int TB>
__device__ __forceinline__ void mma_rs(float (&d)[64], uint32_t a0, uint32_t a1, uint32_t a2, uint32_t a3, uint64_t db, int sc) {
  asm volatile("{\n.reg .pred p;\nsetp.ne.b32 p, %69, 0;\n"
               "wgmma.mma_async.sync.aligned.m64n128k16.f32.bf16.bf16 " D64 ", {%64,%65,%66,%67}, %68, p, 1, 1, %70;\n}"
               : R8(d, 0), R8(d, 8), R8(d, 16), R8(d, 24), R8(d, 32), R8(d, 40), R8(d, 48), R8(d, 56)
               : "r"(a0), "r"(a1), "r"(a2), "r"(a3), "l"(db), "r"(sc), "n"(TB));
}
#define D128 "{%0,%1,%2,%3,%4,%5,%6,%7,%8,%9,%10,%11,%12,%13,%14,%15,%16,%17,%18,%19,%20,%21,%22,%23,%24,%25,%26,%27,%28,%29,%30,%31," \
             "%32,%33,%34,%35,%36,%37,%38,%39,%40,%41,%42,%43,%44,%45,%46,%47,%48,%49,%50,%51,%52,%53,%54,%55,%56,%57,%58,%59,%60,%61,%62,%63," \
             "%64,%65,%66,%67,%68,%69,%70,%71,%72,%73,%74,%75,%76,%77,%78,%79,%80,%81,%82,%83,%84,%85,%86,%87,%88,%89,%90,%91,%92,%93,%94,%95," \
             "%96,%97,%98,%99,%100,%101,%102,%103,%104,%105,%106,%107,%108,%109,%110,%111,%112,%113,%114,%115,%116,%117,%118,%119,%120,%121,%122,%123,%124,%125,%126,%127}"
#define R128(d, e) R8(d, 0), R8(d, 8), R8(d, 16), R8(d, 24), R8(d, 32), R8(d, 40), R8(d, 48), R8(d, 56), \
                   R8(e, 0), R8(e, 8), R8(e, 16), R8(e, 24), R8(e, 32), R8(e, 40), R8(e, 48), R8(e, 56)
__device__ __forceinline__ void mma256_ss(float (&d)[64], float (&e)[64], uint64_t da, uint64_t db, int sc) {
  asm volatile("{\n.reg .pred p;\nsetp.ne.b32 p, %130, 0;\n"
               "wgmma.mma_async.sync.aligned.m64n256k16.f32.bf16.bf16 " D128 ", %128, %129, p, 1, 1, 0, 1;\n}"
               : R128(d, e) : "l"(da), "l"(db), "r"(sc));
}
__device__ __forceinline__ void mma256_rs(float (&d)[64], float (&e)[64], uint32_t a0, uint32_t a1, uint32_t a2, uint32_t a3, uint64_t db) {
  asm volatile("{\n.reg .pred p;\nsetp.ne.b32 p, 1, 0;\n"
               "wgmma.mma_async.sync.aligned.m64n256k16.f32.bf16.bf16 " D128 ", {%128,%129,%130,%131}, %132, p, 1, 1, 1;\n}"
               : R128(d, e) : "r"(a0), "r"(a1), "r"(a2), "r"(a3), "l"(db));
}
template <int N> __device__ __forceinline__ void keep(float (&a)[N]) {
#pragma unroll
  for (int i = 0; i < N; i++) asm volatile("" : "+f"(a[i])::"memory");
}
template <int N> __device__ __forceinline__ void keep(uint32_t (&a)[N]) {
#pragma unroll
  for (int i = 0; i < N; i++) asm volatile("" : "+r"(a[i])::"memory");
}

#define STAMP(idx) do {} while (0)
#define PROF(grp, cond, idx) do {} while (0)

constexpr float SCL2 = 1.4426950408889634f * 0.08838834764831845f;

__device__ __forceinline__ void pack_p(const float (&s)[64], uint32_t (&p)[32]) {
#pragma unroll
  for (int i = 0; i < 32; i++) p[i] = pack_bf(s[2 * i], s[2 * i + 1]);
}

__device__ __forceinline__ void issue_qk(float (&s)[64], uint32_t q0, uint32_t q1, uint32_t kslot) {
  const uint64_t db = make_desc(kslot, 16, 1024), da0 = make_desc(q0, 16, 1024), da1 = make_desc(q1, 16, 1024);
#pragma unroll
  for (int kk = 0; kk < 8; kk++) mma_ss<0>(s, (kk < 4 ? da0 : da1) + (kk & 3) * 2, db + (kk >> 2) * 1024 + (kk & 3) * 2, kk != 0);
}
__device__ __forceinline__ void issue_pv(float (&o)[64], uint32_t (&p)[32], uint32_t vslot, int acc) {
  uint64_t db = make_desc(vslot, 16384, 1024);
#pragma unroll
  for (int kk = 0; kk < 8; kk++)
    mma_rs<1>(o, p[4 * kk], p[4 * kk + 1], p[4 * kk + 2], p[4 * kk + 3], db + kk * 128, kk == 0 ? acc : 1);
}

template <int H>
__device__ __forceinline__ void store_chunk(const float (&a)[64], uint32_t addr) {
#pragma unroll
  for (int i = 8 * H; i < 8 * H + 8; i += 2)
    stmatrix4(addr ^ ((i & 7) << 4), pack_bf(a[4 * i], a[4 * i + 1]), pack_bf(a[4 * i + 2], a[4 * i + 3]),
              pack_bf(a[4 * i + 4], a[4 * i + 5]), pack_bf(a[4 * i + 6], a[4 * i + 7]));
}
template <int H>
__device__ __forceinline__ void store_chunk(const float (&a)[64], float i0, float i1, uint32_t addr) {
#pragma unroll
  for (int i = 8 * H; i < 8 * H + 8; i += 2)
    stmatrix4(addr ^ ((i & 7) << 4), pack_bf(a[4 * i] * i0, a[4 * i + 1] * i0), pack_bf(a[4 * i + 2] * i1, a[4 * i + 3] * i1),
              pack_bf(a[4 * i + 4] * i0, a[4 * i + 5] * i0), pack_bf(a[4 * i + 6] * i1, a[4 * i + 7] * i1));
}
__device__ __forceinline__ float inv_quad_sum(float l) {
  l += __shfl_xor_sync(0xffffffffu, l, 1);
  l += __shfl_xor_sync(0xffffffffu, l, 2);
  return rcp(l);
}

__device__ __forceinline__ void write_table(uint32_t table, bool ca, uint32_t t, const uint4& m0, const uint4& m1) {
  float c0 = untag_sum(m0.x, m1.x), c1 = untag_sum(m0.y, m1.y), c2 = untag_sum(m0.z, m1.z), c3 = untag_sum(m0.w, m1.w);
  if (ca) { c0 = 1.f + rbf(c0); c1 = 1.f + rbf(c1); c2 = 1.f + rbf(c2); c3 = 1.f + rbf(c3); }
  const uint32_t d = table + (t >> 2) * 64 + (t & 1) * 32 + (t & 2) * 2 + (ca ? 0 : 8);
  sts1(d, pack_bf(c0, c1));
  sts1(d + 16, pack_bf(c2, c3));
}

__device__ __forceinline__ void ln_scalars(float mean, float var, float& mb, float& sd) {
  mb = rbf(mean);
  float r; asm("sqrt.approx.ftz.f32 %0, %1;" : "=f"(r) : "f"(rbf(rbf(var) + 1e-5f)));
  sd = rbf(r);
}

__global__ void __cluster_dims__(2, 1, 1) __launch_bounds__(384, 1) fused_kernel(const __grid_constant__ Maps maps, const Ptrs P) {
  extern __shared__ __align__(1024) uint8_t smem_raw[];
  const uint32_t base = smem_u32(smem_raw);
  const int tid = threadIdx.x, lane = tid & 31;
  const int warp = __shfl_sync(0xffffffffu, tid >> 5, 0);
  const int b = blockIdx.x;
  PROF(31, tid == 0, 0);

  if (b >= NMAIN) {
    float* sc = reinterpret_cast<float*>(smem_raw);
    float* red = sc + DM;
    for (int k = tid; k < DM; k += 384) sc[k] = rbf(silu_f(__bfloat162float(P.c[k])));
    __syncthreads();
    if (tid < 256) {
      const int col = 2048 + (b - NMAIN) * 1024 + (tid & 127) * 8, r0 = (tid >> 7) * 512;
      float acc[8];
#pragma unroll
      for (int e = 0; e < 8; e++) acc[e] = 0.f;
#pragma unroll 1
      for (int r = r0; r < r0 + 512; r += HU) {
        uint4 w[HU];
#pragma unroll
        for (int u = 0; u < HU; u++) w[u] = ldg_stream4(P.w_mod + (size_t)(r + u) * NMOD + col);
#pragma unroll
        for (int u = 0; u < HU; u++) {
          float s = sc[r + u];
          acc[0] += s * bf_lo(w[u].x); acc[1] += s * bf_hi(w[u].x); acc[2] += s * bf_lo(w[u].y); acc[3] += s * bf_hi(w[u].y);
          acc[4] += s * bf_lo(w[u].z); acc[5] += s * bf_hi(w[u].z); acc[6] += s * bf_lo(w[u].w); acc[7] += s * bf_hi(w[u].w);
        }
      }
      if (tid >= 128) {
#pragma unroll
        for (int e = 0; e < 8; e++) red[(tid & 127) * 8 + e] = acc[e];
      }
      const uint32_t tag = ld_relaxed(&g_epoch) % 3 + 1;
      bar_sync(1, 256);
      if (tid < 128) {
        uint32_t o[8];
#pragma unroll
        for (int e = 0; e < 8; e++) o[e] = __float_as_uint(rbf(acc[e] + red[tid * 8 + e])) | tag;
        st_relaxed4(g_mod + col, o[0], o[1], o[2], o[3]);
        st_relaxed4(g_mod + col + 4, o[4], o[5], o[6], o[7]);
        const uint4 wr = ldg_nc4(P.w_r + tid * 8);
        const uint32_t wv[4] = {wr.x, wr.y, wr.z, wr.w};
        float dsum = 0.f;
#pragma unroll
        for (int e = 0; e < 8; e++) {
          const float m = bf_hi(o[e]);
          dsum += (b == NMAIN + 2 ? rbf(1.f + m) : m) * ((e & 1) ? bf_hi(wv[e >> 1]) : bf_lo(wv[e >> 1]));
        }
#pragma unroll
        for (int k = 16; k > 0; k >>= 1) dsum += __shfl_xor_sync(0xffffffffu, dsum, k);
        if (lane == 0) st_relaxed(g_mod + (b - NMAIN) * 4 + warp, tagf(dsum, tag));
      }
    }
    PROF(2, tid == 0, 1);
    return;
  }

  const int rank = b & 1;
  const int rb = ((b >> 4) << 1) | rank, cj = (b >> 1) & 7;
  const bool late = b & 4;
  const uint32_t bfull = base + OFF_BAR, bempty = bfull + NSLOT * 8;
  const uint32_t gfull = bempty + NSLOT * 8, gempty = gfull + 32;
  const uint32_t bar_ofull = gempty + 32;
  const uint32_t bar_ofree = bar_ofull + 32;
  const uint32_t bar_par = bar_ofree + 32;
  const uint32_t bar_mod = bar_par + 8;
  const uint32_t bar_pread = bar_mod + 8;
  const uint32_t bar_xres = bar_pread + 8;
  const uint32_t bar_ring = bar_xres + 8;
  const uint32_t bar_box = bar_ring + 24;
  const uint32_t bar_go = bar_box + 96;
  const uint32_t bar_go2 = bar_go + 16;
  const uint32_t bar_cnt = bar_go + 24;
  const uint32_t xfull = bar_go + 40, xempty = xfull + 32;
  const uint32_t bar_hw = xempty + 32, bar_hx = bar_hw + 8;
  const uint32_t bar_hpub = bar_hx + 16;
  const uint32_t bar_win = bar_hpub + 16;
  const uint32_t bar_rx = bar_win + 8;
  const uint32_t bar_sel = bar_rx + 8;
  const uint32_t bar_gate = bar_sel + 8;
  const uint32_t bar_rel = bar_gate + 8;
  const uint32_t bar_od = bar_rel + 8;
  const uint32_t bar_mod2 = bar_od + 8;
  const uint32_t bar_res = bar_go + 8;
  const uint32_t stage = base + OFF_STAGE, par = base + OFF_PAR;

  if (warp == 10 && elect_one()) prefetch_map(&maps.wm);
  if (warp == 8 && elect_one()) {
    for (int s = 0; s < NSLOT; s++) { mbar_init(bfull + s * 8, 1); mbar_init(bempty + s * 8, 16); }
    for (int s = 0; s < 4; s++) { mbar_init(gfull + s * 8, 1); mbar_init(gempty + s * 8, 16); mbar_init(xfull + s * 8, 1); mbar_init(xempty + s * 8, 8); mbar_init(bar_ofree + s * 8, 1); mbar_init(bar_ofull + s * 8, 128); }
    mbar_init(bar_par, 64); mbar_init(bar_mod, 256); mbar_init(bar_pread, 2); mbar_init(bar_xres, 1);
    mbar_init(bar_ring, 8); mbar_init(bar_ring + 8, 8); mbar_init(bar_ring + 16, 8);
    mbar_init(bar_go, 1); mbar_init(bar_go2, 1); mbar_init(bar_cnt, 1); mbar_init(bar_cnt + 8, 1); mbar_init(bar_hpub, 8); mbar_init(bar_hpub + 8, 8); mbar_init(bar_res, 1); mbar_init(bar_win, 1); mbar_init(bar_rx, 1); mbar_init(bar_sel, 64); mbar_init(bar_gate, 8); mbar_init(bar_rel, 8); mbar_init(bar_od, 1); mbar_init(bar_mod2, 64);
    for (int s = 0; s < 12; s++) mbar_init(bar_box + s * 8, 1);
    asm volatile("fence.mbarrier_init.release.cluster;" ::: "memory");
    prefetch_map(&maps.x); prefetch_map(&maps.wq); prefetch_map(&maps.k); prefetch_map(&maps.v);
  }
  if (warp == 9 && elect_one()) {
    mbar_init(bar_hw, 1); mbar_init(bar_hx, 1); mbar_init(bar_hx + 8, 1);
    asm volatile("fence.mbarrier_init.release.cluster;" ::: "memory");
    mbar_expect_tx(bar_hw, 32768);
    mbar_expect_tx(bar_hx, 16384);
    mbar_expect_tx(bar_hx + 8, 16384);
    const __nv_bfloat16* xs = P.x + (size_t)(rb * 128 + cj * 16) * DM;
    bulk_load(base + 2 * GST_BYTES, xs, 16384, bar_hx);
    if (!late) {
      tma2d(stage, &maps.wm, (b >> 1) * 32, rank * 512, bar_hw);
      tma2d(stage + 16384, &maps.wm, (b >> 1) * 32, rank * 512 + 256, bar_hw);
    }
    bulk_load(base + 3 * GST_BYTES, xs + 8 * DM, 16384, bar_hx + 8);
  }
  cluster_arrive();

  if (warp >= 8) {
    asm volatile("setmaxnreg.dec.sync.aligned.u32 40;");
    if (warp < 10) bar_arrive(1, 320);
    const uint32_t epoch = ld_relaxed(&g_epoch);
    cluster_wait();
    if (warp == 8) {
      const int kvrow = (cj >> 1) * SK + (SK - WIN);
      int wch = cj * 8 + rank * 2;
#pragma unroll 1
      for (int ps = 0; ps < 3; ps++) {
        const CUtensorMap* mw = ps == 2 ? &maps.wo : &maps.wq;
        const uint32_t xt = ps == 1 ? XT1 : XT2, wt = ps == 0 ? WT0 : (ps == 1 ? WT1 : WT2);
        const int nst = ps == 2 ? 32 : 16;
#pragma unroll 1
        for (int i = 0; i < nst; i++) {
          const uint32_t bf = gfull + (i & 3) * 8;
          const int kt = ps == 2 ? (((cj & 1) * 4 + ((i >> 1) & 3)) * 4 + (i >> 3)) * 2 + (i & 1) : (ps ? i : slice_of(i) + (b & 14)) & 15;
          const uint32_t wd = base + unit_of(wt, i & 3) + rank * UNIT, xd = base + unit_of(xt, i & 3);
          const uint8_t* xs = g_act + (uint32_t)(rb * 80 + (ps - 1) * 16 + kt) * UNIT;
          if (ps == 0 && i == HD) mbar_wait(bar_mod, 0);
          if (ps == 2 && (i & 7) == 0 && i != 8) mbar_wait(i ? bar_cnt + i - 16 : bar_ofree + 24, 0);
          if ((i & 7) == 0) fence_async();
          if (i == RES0) mbar_wait(bar_res, 0);
          mbar_wait(bf, ((i >> 2) & 1) ^ 1);
          if (elect_one()) {
            mbar_expect_tx(bf, ps ? GST_BYTES : 2 * UNIT);
            if (ps && i < 2) bulk_load_stream(xd, xs, UNIT, bf);
            mbar_arrive_pred(bar_go, i == GOST);
            mbar_arrive_pred(bar_go2, ps == 1 && i == PG0);
            mbar_arrive_pred(bar_od, ps && i == (ps == 1 ? ODS1 : ODS) + 1);
            if (i == RES0) mbar_expect_tx(bar_xres, 32768);
          }
          const int wk = (i == 31 ? kt ^ (rank * 32) : kt) * 64, wc = i == 31 ? cj * 2 : wch;
          const uint64_t xp = i == 31 ? l2_normal() : l2_stream();
          mbar_wait(ps && i < 4 ? bempty + i * 8 : gempty + (i & 3) * 8, ((i >> 2) & 1) ^ 1);
          if (elect_one()) {
            tma3d_mc<true>(wd, mw, 0, wk, wc, bf);
            if (ps && i > 2) bulk_load_stream(xd, xs, UNIT, bf, xp);
            if (i == RES0 || i == RES1) tma2d(base + OFF_RES + (i == RES1) * UNIT, &maps.x, cj * 128 + (i == RES1) * 64, rb * 128, bar_xres);
          }
          if (ps && i == 2) {
            mbar_wait(bar_ofree + (ps - 1) * 16, 0);
            if (elect_one()) bulk_load_stream(xd, xs, UNIT, bf);
          }
        }
        if (ps == 2) break;
        wch = ps ? ((wch >> 3) ^ rank) * 2 : wch + 4;
#pragma unroll 1
        for (int u = 0; u < 16; u++) {
          const bool isk = (u == 0) || ((u & 1) && u < 15);
          const int blk = (isk ? (u + 1) >> 1 : (u == 15 ? 7 : (u >> 1) - 1)) & 3;
          const uint32_t sl = base + unit_of(ps ? AT1 : AT0, u & 3) + rank * UNIT, bf = bfull + (u & 3) * 8;
          mbar_wait(bf, ((u >> 2) & 1) ^ 1);
          if (elect_one()) mbar_expect_tx(bf, SLOT_BYTES);
          mbar_wait(u < 4 ? gempty + ((u + 1) >> 1) * 8 : bempty + (u & 3) * 8, ((u >> 2) & 1) ^ 1);
          if (elect_one()) {
            if (ps && u >= 7 && u != 8) tma3d_mc<true>(sl, isk ? &maps.k : &maps.v, 0, kvrow + blk * 128, rank, bf);
            else tma3d_mc<false>(sl, isk ? &maps.k : &maps.v, 0, kvrow + blk * 128, rank, bf);
          }
        }
      }
      if (elect_one()) mbar_expect_tx(bar_rx, UNIT);
      mbar_wait(bar_rel, 0);
      if (elect_one()) {
        bulk_load_stream(base + UNIT, g_act + (uint32_t)(rb * 80 + 16 + 63 - (cj & 1) * 32) * UNIT, UNIT, bar_rx);
      }
      if (b < NFFN) {
#pragma unroll 1
        for (int u = 0; u < 12; u++) {
          const uint32_t dst = base + unit_of(u < 4 ? FT_G : (u < 8 ? FT_U : FT_D), u & 3);
          if (elect_one()) mbar_expect_tx(bar_box + u * 8, UNIT);
          if (u == 0 || u == 2 || u == 8) mbar_wait(bar_ring + (u == 8 ? 16 : u * 4), 0);
          const int fp = u < 8 ? FPACE0 : FPACE;
          if (u >= fp) mbar_wait(bar_box + (u - fp) * 8, 0);
          if (elect_one()) {
            if (u < 8) tma2d(dst, u < 4 ? &maps.wg : &maps.wu, b * 32, (u & 3) * 256, bar_box + u * 8);
            else tma3d(dst, &maps.wd, 0, b * 32, (u - 8) * 4, bar_box + u * 8);
          }
        }
      }
    } else if (warp == 9) {
      const uint32_t target = 8 * (epoch + 1);
      uint32_t hmask = 0;
#pragma unroll 1
      for (int i = 0; i < 16; i++) {
        if (i == HDX) mbar_wait(bar_mod, 0);
        const int kt = (2 * cj + slice_of(i)) & 15;
        const uint32_t need = i == 15 ? 0xffffu : 1u << kt;
        if (i >= NRS && (hmask & need) != need) {
          uint32_t n = 0;
          do { hmask = __ballot_sync(0xffffffffu, ld_acquire(&g_cnt_h[rb * 32 + (lane & 15)]) == epoch + 1); watchdog(n); } while ((hmask & need) != need);
          PROF(1, lane == 0 && i == NRS, 26);
          fence_async();
        }
        mbar_wait(xempty + (i & 3) * 8, ((i >> 2) & 1) ^ 1);
        if (elect_one()) {
          mbar_expect_tx(xfull + (i & 3) * 8, UNIT);
          if (i < NRS) tma2d(base + (i & 3) * GST_BYTES, &maps.x, kt * 64, rb * 128, xfull + (i & 3) * 8);
          else bulk_load_stream(base + (i & 3) * GST_BYTES, g_act + (uint32_t)(rb * 80 + kt) * UNIT, UNIT, xfull + (i & 3) * 8);
        }
      }
      prefetch_map(&maps.wo);
#pragma unroll 1
      for (int t = 0; t < 4; t++) {
        if (t & 1) mbar_wait(bar_od, t >> 1);
        const int ops = OPS >> (t & 1);
#pragma unroll 1
        for (int p = 0; p < 32768; p += ops) {
          const uint32_t w = p >> 14, c = (p >> 13) & 1, off = w * 8192 + (p & 8191);
          mbar_wait(bar_ofull + (t & 1) * 16 + w * 8, t >> 1);
          if (elect_one()) {
            bulk_store(g_act + (uint32_t)(rb * 80 + 16 + (cj * 4 + t) * 2 + c) * UNIT + off, base + unit_of(QT, 2 * t + c) + off, ops);
            asm volatile("cp.async.bulk.commit_group;" ::: "memory");
            asm volatile("cp.async.bulk.wait_group.read 0;" ::: "memory");
          }
        }
        if (elect_one()) {
          mbar_arrive(t < 3 ? bar_ofree + t * 8 : bar_res);
          asm volatile("cp.async.bulk.wait_group 0;" ::: "memory");
          fence_async();
          red_release(&g_cnt_o[((rb * 4 + t) * 2 + (cj >> 2)) * 32], 2);
        }
        if (t) {
          wait_counter(&g_cnt_o[(rb * 8 + 2 * t + (cj & 1)) * 32], target);
          if (t & 1) wait_counter(&g_cnt_o[(rb * 8 + (t == 1 ? cj & 1 : 7 - (cj & 1))) * 32], target);
          if (elect_one()) mbar_arrive(t == 1 ? bar_ofree + 24 : bar_cnt + t * 8 - 16);
        }
      }
      PROF(2, lane == 0, 27);
      const uint32_t tag = epoch % 3 + 1;
      const uint32_t* inbox = g_cand + (b >> 1) % CR * 512 + (lane & 15) * CS;
      mbar_wait(bar_ring + 16, 0);
      uint32_t c0 = ld_relaxed(inbox), n = 0;
#define CAND_STEP(cv)                                                                                        \
      {                                                                                                      \
        const bool valid = (cv & 3u) == tag, all = __all_sync(0xffffffffu, valid);                           \
        const uint32_t best = __reduce_max_sync(0xffffffffu, valid ? cv : 0u);                               \
        const uint32_t blk = __ffs(__ballot_sync(0xffffffffu, cv == best)) - 1;                              \
        if (best) sts2(par + PAR_CONST + 56, best, (blk << 7 | (~best >> 2 & 127)) | (all ? 0x1800 : 0x800)); \
        if (all) break;                                                                                      \
        cv = ld_relaxed(inbox);                                                                              \
      }
      while (true) { CAND_STEP(c0) watchdog(n); }
    } else {
      const int t2 = tid - 320;
      if (late && warp == 10) {
        mbar_wait(bar_hx, 0);
        if (elect_one()) {
          tma2d(stage, &maps.wm, (b >> 1) * 32, rank * 512, bar_hw);
          tma2d(stage + 16384, &maps.wm, (b >> 1) * 32, rank * 512 + 256, bar_hw);
        }
      }
      {
        const uint32_t tag = epoch % 3 + 1;
        mbar_wait(bar_hx + 8, 0);
        mbar_wait(bar_hw, 0);
        __nanosleep(late ? OSL2 : OSL);
        {
          const uint32_t t7 = (warp & 1) * 64 + (lane >> 4) * 32 + 16 + (lane & 15);
          const uint32_t* pm = g_modp + ((cj * 128 + t7 * 4) & (DM - 1));
          uint4 m0, m1, m2, m3;
          uint32_t n = 0;
          do {
            m0 = ld_relaxed4(pm); m1 = ld_relaxed4(pm + 2 * DM); m2 = ld_relaxed4(pm + DM); m3 = ld_relaxed4(pm + 3 * DM);
            watchdog(n);
          } while (!__all_sync(0xffffffffu, tag_ok(m0, tag) && tag_ok(m1, tag) && tag_ok(m2, tag) && tag_ok(m3, tag)));
          write_table(par, false, t7, m0, m1);
          write_table(par, true, t7, m2, m3);
          mbar_arrive(bar_mod2);
        }
      }
      mbar_wait(bar_hpub + (warp & 1) * 8, 0);
      PROF(1, t2 == 0, 24);
#pragma unroll 1
      for (int c = 0; c < 8; c++) {
        const uint32_t off = (warp & 1) * UNIT + c * 2048 + lane * 16;
        uint8_t* dst = g_act + (uint32_t)(rb * 80 + cj * 2) * UNIT + off;
        const uint4 v0 = lds4(stage + off), v1 = lds4(stage + off + 512), v2 = lds4(stage + off + 1024), v3 = lds4(stage + off + 1536);
        stg4(dst, v0); stg4(dst + 512, v1); stg4(dst + 1024, v2); stg4(dst + 1536, v3);
      }
      __syncwarp();
      PROF(1, t2 == 0, 15);
      if (lane == 0) {
        mbar_arrive(bar_pread);
        red_release(&g_cnt_h[rb * 32 + cj * 2 + (warp & 1)], 1);
        PROF(1, t2 == 0, 25);
        prefetch_map(&maps.wg); prefetch_map(&maps.wu); prefetch_map(&maps.wd); prefetch_map(&maps.out);
      }
      __syncwarp();
      if (b < NFFN) {
        mbar_wait(bar_go2, 0);
        const __nv_bfloat16* pg = ((b & 1) ? P.w_up : P.w_gate) + (b >> 1) * 64 + (size_t)t2 * FF;
        const __nv_bfloat16* pd = P.w_down + (size_t)b * 32768 + t2 * 64;
        PROF(2, t2 == 0, 13);
#pragma unroll 1
        for (int i = 0; i < WN; i += WB) {
          uint32_t v[WB];
#pragma unroll
          for (int u = 0; u < WB; u++) {
            const int k = i + u;
            asm volatile("ld.global.cg.L2::128B.u32 %0, [%1];" : "=r"(v[u]) : "l"(k < 16 ? pg + (size_t)k * 64 * FF : pd + (k - 16) * 4096));
          }
#pragma unroll
          for (int u = 1; u < WB; u++) v[0] ^= v[u];
          sts1(par + PAR_SINK + t2 * 4, v[0]);
        }
        PROF(2, t2 == 0, 14);
      }
      const uint32_t tag = epoch % 3 + 1;
      mbar_wait(bar_go, 0);
      bar_sync(4, 64);
      if (warp == 10) {
        const uint32_t* src = g_mod + 2 * DM + cj * 128 + lane * 4;
        const uint2 wr = *reinterpret_cast<const uint2*>(P.w_r + cj * 128 + lane * 4);
        uint4 vga, vsb, vcb, vgb;
        uint32_t n = 0;
        do {
          vga = ld_relaxed4(src); vsb = ld_relaxed4(src + DM); vcb = ld_relaxed4(src + 2 * DM); vgb = ld_relaxed4(src + 3 * DM);
          watchdog(n);
        } while (!__all_sync(0xffffffffu, tag_ok(vga, tag) && tag_ok(vsb, tag) && tag_ok(vcb, tag) && tag_ok(vgb, tag)));
        const float c0 = rbf(1.f + bf_hi(vcb.x)), c1 = rbf(1.f + bf_hi(vcb.y)), c2 = rbf(1.f + bf_hi(vcb.z)), c3 = rbf(1.f + bf_hi(vcb.w));
        const float a0 = c0 * bf_lo(wr.x), a1 = c1 * bf_hi(wr.x), a2 = c2 * bf_lo(wr.y), a3 = c3 * bf_hi(wr.y);
        const uint32_t h0 = pack_bf(a0, a1), h1 = pack_bf(a2, a3);
        const uint32_t t1 = par + PAR_T1 + (lane >> 2) * 64 + (lane & 1) * 32 + (lane & 2) * 2;
        sts1(t1, h0); sts1(t1 + 8, pack_bf(a0 - bf_lo(h0), a1 - bf_hi(h0)));
        sts1(t1 + 16, h1); sts1(t1 + 24, pack_bf(a2 - bf_lo(h1), a3 - bf_hi(h1)));
        const uint32_t tg = par + PAR_SINK + (lane >> 3) * 64 + (lane & 1) * 32 + (lane & 6) * 2;
        sts1(tg, __byte_perm(vga.x, vga.y, 0x7632)); sts1(tg + 16, __byte_perm(vga.z, vga.w, 0x7632));
        sts4(par + PAR_T2 + lane * 32, make_uint4(pack_bf(c0, c1), __byte_perm(vsb.x, vsb.y, 0x7632), __byte_perm(vgb.x, vgb.y, 0x7632), __byte_perm(vga.x, vga.y, 0x7632)));
        sts4(par + PAR_T2 + lane * 32 + 16, make_uint4(pack_bf(c2, c3), __byte_perm(vsb.z, vsb.w, 0x7632), __byte_perm(vgb.z, vgb.w, 0x7632), __byte_perm(vga.z, vga.w, 0x7632)));
      } else {
        const uint4 g = poll4((lane & 8) ? g_mod + 8 - (lane & 1) * 4 : g_mod + 5 * DM + (b >> 4) * 128 + (lane & 7) * 16 + (b & 12), tag);
        sts1(par + PAR_CONST + 60, 0);
        if (lane < 8) sts1(par + PAR_CONST + 16 + lane * 4, (b & 2) ? ((b & 1) ? g.w : g.z) : ((b & 1) ? g.y : g.x));
        else if (lane < 10) sts2(par + PAR_CONST + (lane - 8) * 8, __float_as_uint(untag_sum(g.x, g.y) + untag_sum(g.z, g.w)), epoch);
      }
      __syncwarp();
#pragma unroll 1
      for (int q = 0; q < 32; q++) {
        st_b128(g_xch + ((size_t)b * 8 * 256 + q * 64 + t2) * 4, (epoch & 1) << 16, 0, 0, 0);
        __nanosleep(RSL);
      }
      for (int q = 0; q < 2; q++) st_relaxed4(g_stats + ((size_t)cj * SEQ + rb * 128 + q * 64 + t2) * 4, 0, 0, 0, 0);
      if (b < NFFN)
        for (int q = 0; q < 2; q++) st_relaxed4(ypart_slot(b, q * 64 + t2), 0, 0, 0, 0);
      st_relaxed4(g_row + rb * 2 * DM + (t2 >> 5) * DM + cj * 128 + (t2 & 31) * 4, 0, 0, 0, 0);
      __threadfence();
      mbar_arrive(bar_par);
      mbar_wait(bar_gate, 0);
      uint32_t have = 0, n = 0;
      while (true) {
        const uint32_t st = lds1(par + PAR_CONST + 60) >> 7;
        if ((st & 31) != have) {
          const uint32_t* hsrc = g_row + (st & 15) * 2 * DM + t2 * 4;
          uint4 hv[4];
          bool ok = true;
#pragma unroll
          for (int i = 0; i < 4; i++) hv[i] = ld_pairs(hsrc + i * 256);
#pragma unroll
          for (int i = 0; i < 4; i++) {
            sts2(base + ((FT_G >> i * 4) & 15) * UNIT + (warp & 1) * 8192 + 256 + lane * 8, hv[i].x, hv[i].z);
            ok = ok && hv[i].y == tag && hv[i].w == tag;
          }
          have = __all_sync(0xffffffffu, ok) ? st & 31 : 0;
        }
        if ((st ^ have) == 32) break;
        watchdog(n);
      }
      mbar_arrive(bar_sel);
    }
    __syncwarp();
    cluster_arrive();
    {
      const uint32_t tag = epoch % 3 + 1, t3 = tid - 256;
      mbar_wait(bar_win, 0);
      uint2 win = lds2(par + PAR_CONST + 56);
      win.y &= 0x7ff;
      const uint32_t* fsrc = g_row + (win.y >> 7) * 2 * DM + (b >> 4) * 128 + (t3 & 7) * 16 + (b & 6) * 2 + ((b >> 2) & 2);
      const uint32_t* ysrc = ypart_slot(min(t3, NFFN - 1), b);
      uint2 fh = ld_pair(fsrc), fx = ld_pair(fsrc + DM);
      uint4 ya = ld_b128(ysrc);
      const float rwin = __uint_as_float(((int)win.x < 0 ? win.x & 0x7fffffffu : ~win.x) & ~0x1ffu);
      const float rs = rbf(rcp(1.f + __expf(-rbf(rwin))));
      uint32_t n = 0;
      while (__any_sync(0xffffffffu, fh.y != tag || fx.y != tag)) { fh = ld_pair(fsrc); fx = ld_pair(fsrc + DM); watchdog(n); }
      while (true) {
        const bool miss = ((ya.x & 1) | (ya.y & 1) << 1) != tag;
        if (!__any_sync(0xffffffffu, miss)) break;
        if (miss) ya = ld_b128(ysrc);
        watchdog(n);
      }
      PROF(8, t3 == 0, 5);
      float y[8] = {bf_lo(ya.x & ~1u), bf_hi(ya.x), bf_lo(ya.y & ~1u), bf_hi(ya.y), bf_lo(ya.z), bf_hi(ya.z), bf_lo(ya.w), bf_hi(ya.w)};
#pragma unroll
      for (int h = 4; h > 0; h >>= 1) {
        const bool up = lane & (h * 2);
#pragma unroll
        for (int e = 0; e < h; e++) y[e] = (up ? y[e + h] : y[e]) + __shfl_xor_sync(0xffffffffu, up ? y[e] : y[e + h], h * 2);
      }
      y[0] += __shfl_xor_sync(0xffffffffu, y[0], 1);
      if (!(lane & 1)) sts1(par + PAR_RED + 64 + t3 * 2, __float_as_uint(y[0]));
      bar_sync(4, 128);
      if (t3 < 8) {
        float y0 = 0.f;
#pragma unroll
        for (int w7 = 0; w7 < 7; w7++) y0 += __uint_as_float(lds1(par + PAR_RED + 64 + w7 * 32 + t3 * 4));
        const uint32_t gv = lds1(par + PAR_CONST + 16 + t3 * 4);
        const uint32_t upd = hmul2(pack_bf(y0, y0), pack_bf(rs, rs));
        const uint32_t r = hadd2(fx.x, hmul2(__byte_perm(gv, gv, 0x3232), hadd2(fh.x, upd)));
        reinterpret_cast<uint16_t*>(P.out)[(size_t)win.y * DM + (b >> 4) * 128 + t3 * 16 + (b & 15)] = (b & 1) ? r >> 16 : r;
        if (b == 0 && t3 == 0) st_relaxed(&g_epoch, epoch + 1);
      }
      PROF(31, t3 == 0, 36);
    }
    cluster_wait();
  } else {
    const int wg = warp >> 2;

    uint32_t tag;
    {
      uint32_t* const pmod = g_modp + rank * 2 * DM + (b >> 1) * 32 + lane;
      uint32_t* const pln = g_ln1 + (rb * 128 + cj * 16 + warp) * 4;
      uint32_t sc[8];
#pragma unroll
      for (int k = 0; k < 8; k++) sc[k] = ldg_nc1(P.c + rank * 512 + warp * 64 + k * 8 + (lane & 3) * 2);
      const uint32_t epoch = ld_relaxed(&g_epoch);
      if (warp == 0) st_relaxed(pmod, 0);
      if (lane == 0) { st_b128(pln, 0, 0, 0, 0); st_b128(pln + 32, 0, 0, 0, 0); }
      asm volatile("setmaxnreg.inc.sync.aligned.u32 232;");
      bar_sync(1, 320);
#pragma unroll
      for (int k = 0; k < 8; k++) sc[k] = pack_bf(silu_f(bf_lo(sc[k])), silu_f(bf_hi(sc[k])));
      keep(sc);
      tag = epoch % 3 + 1;
#pragma unroll
      for (int part = 0; part < 4; part++) {
        if (!(part & 1)) {
          const uint32_t xa = base + (2 + part / 2) * GST_BYTES + warp * 2048 + lane * 16;
          mbar_wait(bar_hx + part * 4, 0);
          float s0 = 0.f, s1 = 0.f, q0 = 0.f, q1 = 0.f;
#pragma unroll
          for (int q = 0; q < 4; q++) {
            const uint4 xv = lds4(xa + q * 512);
            const uint32_t u[4] = {xv.x, xv.y, xv.z, xv.w};
#pragma unroll
            for (int e = 0; e < 4; e++) { const float lo = bf_lo(u[e]), hi = bf_hi(u[e]); s0 += lo; s1 += hi; q0 += lo * lo; q1 += hi * hi; }
          }
          s0 += s1; q0 += q1;
#pragma unroll
          for (int o = 16; o > 0; o >>= 1) { s0 += __shfl_xor_sync(0xffffffffu, s0, o); q0 += __shfl_xor_sync(0xffffffffu, q0, o); }
          const float mean = s0 * (1.f / DM);
          float mb, sd;
          ln_scalars(mean, fmaxf(q0 * (1.f / DM) - mean * mean, 0.f), mb, sd);
          uint32_t ih, il;
          split_inv(sd, ih, il);
          if (lane == 0) st_b128(pln + part * 16, pack_bf(mb, mb), ih, il, tag);
          PROF(1, tid == 0 && part == 2, 4);
        } else if (late == (part == 3)) {
          const uint32_t fr = (lane & 7) + (lane >> 4) * 8, tq = lane & 3;
          const uint32_t wa = stage + warp * 4096 + fr * 64 + ((((lane >> 3) & 1) ^ ((fr >> 1) & 3)) << 4);
          float d0[4] = {0.f, 0.f, 0.f, 0.f}, d1[4] = {0.f, 0.f, 0.f, 0.f};
          mbar_wait(bar_hw, 0);
#pragma unroll
          for (int ks = 0; ks < 4; ks++) {
            uint32_t w[8];
            ldmatrix4t(wa + ks * 1024, w[0], w[1], w[2], w[3]);
            ldmatrix4t((wa ^ 32) + ks * 1024, w[4], w[5], w[6], w[7]);
            mma16816(d0, w[0], w[1], w[2], w[3], sc[2 * ks], sc[2 * ks + 1]);
            mma16816(d1, w[4], w[5], w[6], w[7], sc[2 * ks], sc[2 * ks + 1]);
          }
          sts1(base + 2 * GST_BYTES + warp * 2048 + (tq * 8 + (lane >> 2)) * 4, __float_as_uint((tq & 2) ? ((tq & 1) ? d1[2] : d1[0]) : ((tq & 1) ? d0[2] : d0[0])));
          bar_sync(1, 256);
          if (warp == 0) {
            float s = 0.f;
#pragma unroll
            for (int w8 = 0; w8 < 8; w8++) s += __uint_as_float(lds1(base + 2 * GST_BYTES + w8 * 2048 + lane * 4));
            st_relaxed(pmod, (__float_as_uint(s) & ~3u) | tag);
          }
          PROF(1, tid == 0, 3);
        }
      }
      cluster_wait();
      if (wg == 1) bar_arrive(2, 256);
    }

    float f0 = 0.f, f1 = 0.f;
    const uint32_t rempty = lane < 2 ? mapa(bempty, lane & 1) : 0;
    constexpr uint32_t GE = NSLOT * 8 + 32;
    float o[64], s[64];
#pragma unroll 1
    for (int ps = 0; ps < 3; ps++) {
      {
        const uint32_t xt = ps == 1 ? XT1 : XT2, wt = ps == 1 ? WT1 : WT2;
        const int nst = ps == 2 ? 28 : 14;
        if (ps == 0) {
          float ga[64], gb[64];
#pragma unroll
          for (int i = 0; i < 64; i++) { ga[i] = 0.f; gb[i] = 0.f; }
          uint32_t a[2][16];
          const uint32_t l = fresh_lane();
          uint32_t fa[4];
#pragma unroll
          for (int kk = 0; kk < 4; kk++) fa[kk] = (base + wg * 8192 + frag_offset(warp)) ^ (kk * 32);
          const uint32_t mt = par + (l & 3) * 16;
          auto fetch = [&](int i, uint32_t (&f)[16], uint32_t z) {
            mbar_wait(xfull + (i & 3) * 8, i >> 2);
#pragma unroll
            for (int kk = 0; kk < 4; kk++) ldmatrix4(fa[kk] + (i & 3) * GST_BYTES + z, f[4 * kk], f[4 * kk + 1], f[4 * kk + 2], f[4 * kk + 3]);
          };
          const bool oddw = warp & 2;
          uint4 r0, r1;
          {
            const uint32_t t7 = (warp & 1) * 64 + (l >> 4) * 32 + (l & 15);
            const uint32_t* pm = g_modp + wg * DM + ((cj * 128 + t7 * 4) & (DM - 1));
            const uint32_t* pr = g_ln1 + (rb * 128 + warp * 16 + (l >> 2)) * 4;
            uint4 m0 = make_uint4(tag, tag, tag, tag), m1 = m0;
            if (!oddw) { m0 = ld_relaxed4(pm); m1 = ld_relaxed4(pm + 2 * DM); }
            r0 = ld_b128(pr); r1 = ld_b128(pr + 32);
            fetch(0, a[0], 0); fetch(1, a[1], 0);
            uint32_t n = 0;
            bool written = false;
#pragma unroll 1
            while (true) {
              uint32_t miss;
              asm volatile("{ .reg .pred p0, p1, p2, p3; .reg .b32 t, u;\n"
                           "lop3.b32 t, %1, %2, %19, 0x7e; lop3.b32 u, %3, %4, %19, 0x7e; or.b32 t, t, u; and.b32 t, t, 3; setp.ne.u32 p0, t, 0;\n"
                           "lop3.b32 t, %5, %6, %19, 0x7e; lop3.b32 u, %7, %8, %19, 0x7e; or.b32 t, t, u; and.b32 t, t, 3; setp.ne.u32 p1, t, 0;\n"
                           "setp.ne.u32 p2, %12, %19; setp.ne.u32 p3, %16, %19;\n"
                           "@p0 ld.relaxed.gpu.global.v4.u32 {%1, %2, %3, %4}, [%17];\n"
                           "@p1 ld.relaxed.gpu.global.v4.u32 {%5, %6, %7, %8}, [%17 + 8192];\n"
                           "@p2 ld.relaxed.gpu.global.v4.u32 {%9, %10, %11, %12}, [%18];\n"
                           "@p3 ld.relaxed.gpu.global.v4.u32 {%13, %14, %15, %16}, [%18 + 128];\n"
                           "or.pred p0, p0, p1; or.pred p2, p2, p3; vote.sync.any.pred p0, p0, 0xffffffff; vote.sync.any.pred p2, p2, 0xffffffff;\n"
                           "selp.u32 t, 1, 0, p0; selp.u32 u, 2, 0, p2; or.b32 %0, t, u; }"
                           : "=r"(miss), "+r"(m0.x), "+r"(m0.y), "+r"(m0.z), "+r"(m0.w), "+r"(m1.x), "+r"(m1.y), "+r"(m1.z), "+r"(m1.w),
                             "+r"(r0.x), "+r"(r0.y), "+r"(r0.z), "+r"(r0.w), "+r"(r1.x), "+r"(r1.y), "+r"(r1.z), "+r"(r1.w)
                           : "l"(pm), "l"(pr), "r"(tag) : "memory");
              if (!(miss & 1) && !written) {
                written = true;
                if (!oddw) write_table(par, wg, t7, m0, m1);
                mbar_arrive(bar_mod);
              }
              if (!miss) break;
              watchdog(n);
            }
          }
          const uint32_t zero = r0.w ^ tag;
          auto normalize = [&](uint32_t (&f)[16]) {
#pragma unroll
            for (int k = 0; k < 16; k += 2) { f[k] = ln_norm(f[k], r0.x, r0.y, r0.z); f[k + 1] = ln_norm(f[k + 1], r1.x, r1.y, r1.z); }
          };
          auto modulate = [&](int i, uint32_t (&f)[16]) {
#pragma unroll
            for (int kk = 0; kk < 4; kk++) {
              const uint4 m = lds4(mt + slice_of(i) * 256 + kk * 64);
              f[4 * kk] = hfma2(f[4 * kk], m.x, m.z); f[4 * kk + 1] = hfma2(f[4 * kk + 1], m.x, m.z);
              f[4 * kk + 2] = hfma2(f[4 * kk + 2], m.y, m.w); f[4 * kk + 3] = hfma2(f[4 * kk + 3], m.y, m.w);
            }
            keep(f);
            mbar_arrive_pred(xempty + (i & 3) * 8, l == 0);
          };
          auto publish = [&](int u, uint32_t (&f)[16]) {
#pragma unroll
            for (int kk = 0; kk < 4; kk++) stmatrix4(fa[kk] + OFF_STAGE + u * UNIT, f[4 * kk], f[4 * kk + 1], f[4 * kk + 2], f[4 * kk + 3]);
            __syncwarp();
            mbar_arrive_pred(bar_hpub + u * 8, l == 0);
          };
          auto multiply = [&](int i, uint32_t (&f)[16]) {
            mbar_wait(gfull + (i & 3) * 8, i >> 2);
            const uint64_t db = make_desc(base + (i & 3) * GST_BYTES + UNIT, 8192, 1024);
            wg_fence();
#pragma unroll
            for (int kk = 0; kk < 4; kk++) mma256_rs(ga, gb, f[4 * kk], f[4 * kk + 1], f[4 * kk + 2], f[4 * kk + 3], db + kk * 128);
            wg_commit();
          };
          auto next = [&](int i, uint32_t (&f)[16]) {
            wg_wait<1>();
            mbar_arrive_cl(rempty, GE + ((i + 2) & 3) * 8);
            uint32_t z = zero;
#pragma unroll
            for (int k = 0; k < 16; k += 2) asm volatile("lop3.b32 %0, %1, %2, %0, 0xA8;" : "+r"(z) : "r"(f[k]), "r"(f[k + 1]));
            fetch(i, f, z);
            normalize(f);
            if (i == 2) { keep(f); mbar_wait(bar_mod2, 0); }
            modulate(i, f); multiply(i, f);
          };
          normalize(a[0]); normalize(a[1]);
          keep(a[0]); keep(a[1]);
          mbar_wait(bar_mod, 0);
          PROF(1, tid == 0, 2);
          modulate(0, a[0]); multiply(0, a[0]); publish(0, a[0]);
          modulate(1, a[1]); multiply(1, a[1]);
#pragma unroll 1
          for (int i = 2; i < NRS; i += 2) {
            next(i, a[0]);
            if (i == 2) publish(1, a[0]);
            next(i + 1, a[1]);
          }
          wg_wait<1>();
          mbar_arrive_cl(rempty, GE + ((NRS + 2) & 3) * 8);
#pragma unroll 1
          for (int i = NRS; i < 14; i++) {
            mbar_wait(xfull + (i & 3) * 8, (i >> 2) & 1);
            mbar_wait(gfull + (i & 3) * 8, (i >> 2) & 1);
            const uint32_t xa = base + (i & 3) * GST_BYTES;
            const uint64_t da = make_desc(xa + wg * 8192, 16, 1024), db = make_desc(xa + UNIT, 8192, 1024);
            if (i == 13) bar_sync(2 + wg, 256);
            wg_fence();
#pragma unroll
            for (int kk = 0; kk < 4; kk++) mma256_ss(ga, gb, da + kk * 2, db + kk * 128, 1);
            wg_commit();
            if (i == 13) bar_arrive(3 - wg, 256);
            wg_wait<1>();
            uint32_t z = zero;
#pragma unroll
            for (int k = 0; k < 16; k += 2) asm volatile("lop3.b32 %0, %1, %2, %0, 0xA8;" : "+r"(z) : "r"(a[1][k]), "r"(a[1][k + 1]));
            mbar_arrive_cl(rempty, GE + ((i + 3) & 3) * 8 + z);
            mbar_arrive_pred(xempty + ((i + 3) & 3) * 8, l == 0 && i != NRS);
          }
          mbar_wait(xfull + 16, 1);
          wg_wait<0>();
          keep(ga); keep(gb);
#pragma unroll
          for (int i = 0; i < 64; i++) {
            asm volatile("mov.b32 %0, %1;" : "=f"(s[i]) : "f"(ga[i]));
            asm volatile("mov.b32 %0, %1;" : "=f"(o[i]) : "f"(gb[i]));
          }
        } else {
          float ga[64], gb[64];
#pragma unroll
          for (int i = 0; i < 64; i++) {
            asm volatile("mov.b32 %0, %1;" : "=f"(ga[i]) : "f"(s[i]));
            asm volatile("mov.b32 %0, %1;" : "=f"(gb[i]) : "f"(o[i]));
          }
#pragma unroll 1
          for (int i = 0; i < nst; i++) {
            mbar_wait(gfull + (i & 3) * 8, (i >> 2) & 1);
            const uint64_t da = make_desc(base + unit_of(xt, i & 3) + wg * 8192, 16, 1024), db = make_desc(base + unit_of(wt, i & 3), 8192, 1024);
            if (i == nst - 1) bar_sync(2 + wg, 256);
            wg_fence();
#pragma unroll
            for (int kk = 0; kk < 4; kk++) mma256_ss(ga, gb, da + kk * 2, db + kk * 128, kk ? 1 : i);
            wg_commit();
            if (i == nst - 1) bar_arrive(3 - wg, 256);
            wg_wait<1>();
            mbar_arrive_cl(rempty, GE + ((i + 3) & 3) * 8, i != 0);
            PROF(4, tid == 0 && (i & 3) == 0, 40 + (ps - 1) * 4 + i / 4);
          }
          wg_wait<0>();
          keep(ga); keep(gb);
#pragma unroll
          for (int i = 0; i < 64; i++) {
            asm volatile("mov.b32 %0, %1;" : "=f"(s[i]) : "f"(ga[i]));
            asm volatile("mov.b32 %0, %1;" : "=f"(o[i]) : "f"(gb[i]));
          }
        }
        mbar_arrive_cl(rempty, GE + (ps == 2 ? 24 : 8));
        if (ps == 2) break;
      }
      const uint32_t qw = base + wg * 8192, qt = QT >> (16 * ps), at = ps ? AT1 : AT0;
      {
        const uint32_t wt = ps ? WT1 : WT0;
        const uint64_t da0 = make_desc(qw + unit_of(qt, 2), 16, 1024), da1 = make_desc(qw + unit_of(qt, 3), 16, 1024);
        const uint64_t db0 = make_desc(base + unit_of(wt, 2), 8192, 1024), db1 = make_desc(base + unit_of(wt, 3), 8192, 1024);
        mbar_wait(gfull + 16, 1);
        bar_sync(2 + wg, 256);
        wg_fence();
#pragma unroll
        for (int kk = 0; kk < 4; kk++) mma_ss<1>(s, da0 + kk * 2, db0 + kk * 128, 1);
        wg_commit();
        mbar_wait(xfull + 24, 1);
        mbar_wait(gfull + 24, 1);
        wg_fence();
#pragma unroll
        for (int kk = 0; kk < 4; kk++) mma_ss<1>(s, da1 + kk * 2, db1 + kk * 128, 1);
        wg_commit();
        bar_arrive(3 - wg, 256);
        mbar_wait(ps == 0 ? bar_pread : bar_ofree + 8, 0);
        wg_wait<0>();
        keep(s);
        PROF(2, tid == 0, 8 + ps * 8);
        uint32_t q[32];
        pack_p(s, q);
#pragma unroll
        for (int i = 0; i < 4; i++) stmatrix4((qw + unit_of(qt, 0) + frag_offset(warp)) ^ (i << 5), q[4 * i], q[4 * i + 1], q[4 * i + 2], q[4 * i + 3]);
        keep(q);
        bar_sync(2 + wg, 256);
        wg_fence();
#pragma unroll
        for (int kk = 0; kk < 8; kk++) mma_ss<1>(o, (kk < 4 ? da0 : da1) + (kk & 3) * 2, (kk < 4 ? db0 : db1) + UNIT / 16 + (kk & 3) * 128, 1);
        wg_commit();
        mbar_wait(bfull, 0);
        wg_fence();
        const uint64_t dk = make_desc(base + unit_of(at, 0), 16, 1024);
#pragma unroll
        for (int kk = 0; kk < 8; kk++) mma_rs<0>(s, q[4 * kk], q[4 * kk + 1], q[4 * kk + 2], q[4 * kk + 3], dk + (kk >> 2) * 1024 + (kk & 3) * 2, kk != 0);
        wg_commit();
        bar_arrive(3 - wg, 256);
#pragma unroll
        for (int i = 4; i < 8; i++) stmatrix4((qw + unit_of(qt, 1) + frag_offset(warp)) ^ ((i & 3) << 5), q[4 * i], q[4 * i + 1], q[4 * i + 2], q[4 * i + 3]);
        wg_wait<1>();
        keep(o);
        mbar_arrive_cl(rempty, GE + 16);
        mbar_arrive_cl(rempty, GE + 24);
        store_chunk<0>(o, qw + unit_of(qt, 2) + frag_offset(warp));
        store_chunk<1>(o, qw + unit_of(qt, 3) + frag_offset(warp));
        wg_wait<0>();
        keep(s);
        mbar_arrive_cl(rempty, 0);
      }
      PROF(4, tid == 0 && ps == 1, 61);
      float l0 = 0.f, l1 = 0.f;
      auto step = [&](auto odd_c, const int j, uint32_t (&pw)[32], uint32_t (&pr)[32]) {
        constexpr bool ODD = decltype(odd_c)::value;
        const bool first = !ODD && (j & 2) == 0, last = ODD && j == 7;
        const uint32_t ph = (j >> 1) & 1;
        float i0, i1, a0, a1;
        const bool so = !ODD && j == 4;
        if (so) { i0 = inv_quad_sum(l0); i1 = inv_quad_sum(l1); l0 = 0.f; l1 = 0.f; }
        bool redo = !ODD && (j | ps) == 0;
        while (true) {
          if (redo) {
            float m0 = fmaxf(s[0], s[1]), m1 = fmaxf(s[2], s[3]);
#pragma unroll
            for (int i = 1; i < 16; i++) { m0 = fmaxf(m0, fmaxf(s[4 * i], s[4 * i + 1])); m1 = fmaxf(m1, fmaxf(s[4 * i + 2], s[4 * i + 3])); }
            m0 = fmaxf(m0, __shfl_xor_sync(0xffffffffu, m0, 1)); m1 = fmaxf(m1, __shfl_xor_sync(0xffffffffu, m1, 1));
            m0 = fmaxf(m0, __shfl_xor_sync(0xffffffffu, m0, 2)); m1 = fmaxf(m1, __shfl_xor_sync(0xffffffffu, m1, 2));
            m0 *= SCL2; m1 *= SCL2;
            if (!first) {
              m0 = fmaxf(m0, f0); m1 = fmaxf(m1, f1);
              const float c0 = ex2(f0 - m0), c1 = ex2(f1 - m1);
              l0 *= c0; l1 *= c1;
              wg_wait<0>();
              keep(o);
#pragma unroll
              for (int i = 0; i < 16; i++) { o[4 * i] *= c0; o[4 * i + 1] *= c0; o[4 * i + 2] *= c1; o[4 * i + 3] *= c1; }
            }
            f0 = m0; f1 = m1;
          }
          float b0 = 0.f, b1 = 0.f;
          a0 = 0.f; a1 = 0.f;
#pragma unroll
          for (int i = 0; i < 16; i++) {
            const float e0 = ex2(fmaf(s[4 * i], SCL2, -f0)), e1 = ex2(fmaf(s[4 * i + 1], SCL2, -f0));
            const float e2 = ex2(fmaf(s[4 * i + 2], SCL2, -f1)), e3 = ex2(fmaf(s[4 * i + 3], SCL2, -f1));
            a0 += e0; b0 += e1; a1 += e2; b1 += e3;
            pw[2 * i] = pack_bf(e0, e1); pw[2 * i + 1] = pack_bf(e2, e3);
            if (i == VREL) {
#pragma unroll
              for (int k = 0; k < 2 * VREL + 2; k++) asm volatile("" : "+r"(pw[k])::"memory");
              mbar_wait(bar_mod, 0);
              wg_wait<0>();
              mbar_arrive_cl(rempty, ODD ? 16 : 0, !redo && (ODD || j));
#pragma unroll
              for (int k = 4 * VREL + 4; k < 64; k++) asm volatile("" : "+f"(s[k])::"memory");
            }
          }
          a0 += b0; a1 += b1;
          if (redo) break;
          redo = __any_sync(0xffffffffu, !(a0 + a1 < 0x1p90f) || (!ODD && fminf(a0, a1) < (first ? 0x1p-90f : 0.f)));
          if (!redo) break;
        }
        l0 += a0; l1 += a1;
        keep(pw);
        keep(o);
        if (so) store_chunk<0>(o, i0, i1, qw + unit_of(qt, 0) + frag_offset(warp));
        keep(o);
        if (j == (ODD ? 5 : 0)) { fence_async_smem(); if (ODD) mbar_arrive(bar_ofull + wg * 8); }
        mbar_wait(bfull + (ODD ? 24 : 8), ph);
        bar_sync(2 + wg, 256);
        if (!last) {
          const uint32_t qn = qt >> (j >= 3 ? 8 : 0);
          wg_fence();
          issue_qk(s, qw + unit_of(qn, 0), qw + unit_of(qn, 1), base + unit_of(at, ODD ? 3 : 1));
          wg_commit();
          mbar_wait(bfull + (ODD ? 0 : 16), ODD ? ph ^ 1 : ph);
        }
        if (so) { store_chunk<1>(o, i0, i1, qw + unit_of(qt, 1) + frag_offset(warp)); keep(o); }
        wg_fence();
        issue_pv(o, pw, base + unit_of(at, ODD ? (last ? 3 : 0) : 2), !first);
        wg_commit();
        bar_arrive(3 - wg, 256);
        wg_wait<1>();
        keep(s);
        mbar_arrive_cl(rempty, ODD ? 24 : 8, !last);
        PROF(4, tid == 0 && ps == 1, 51 + j);
      };
      uint32_t pa[32], pb[32];
#pragma unroll 1
      for (int j = 0; j < 8; j += 2) {
        step(std::false_type{}, j, pa, pb);
        step(std::true_type{}, j + 1, pb, pa);
      }
      {
        const float i0 = inv_quad_sum(l0), i1 = inv_quad_sum(l1);
        wg_wait<0>();
        keep(o);
        mbar_arrive_cl(rempty, 24);
        store_chunk<0>(o, i0, i1, qw + unit_of(qt, 2) + frag_offset(warp));
        store_chunk<1>(o, i0, i1, qw + unit_of(qt, 3) + frag_offset(warp));
        fence_async_smem();
        mbar_arrive(bar_ofull + 16 + wg * 8);
      }
      PROF(2, tid == 0, 10 + ps * 8);
    }

    const int ln = fresh_lane(), g = ln >> 2, tq = ln & 3, ct = warp * 32 + ln;
    const bool lane0 = ln == 0;
    const int lrow0 = warp * 16 + g;
    const int grow0 = rb * 128 + lrow0;
    const uint32_t res = base + OFF_RES, trow = res + wg * 8192 + frag_offset(warp);
    uint32_t xr[32];
    uint4 sv[4], own;
    uint32_t* sp[4];
#pragma unroll
    for (int k = 0; k < 4; k++) sp[k] = g_stats + ((((tq >> 1) * 4 + k) ^ cj) * SEQ + grow0 + (tq & 1) * 8) * 4;
    {
      const uint64_t da = make_desc(base + wg * 8192, 16, 1024), db = make_desc(base, 8192, 1024);
      constexpr int U = UNIT / 16;
#define HALF_STAGE(acc, xu, wu) _Pragma("unroll") for (int kk = 0; kk < 4; kk++) mma_ss<1>(acc, da + (xu) * U + kk * 2, db + (wu) * U + kk * 128, 1)
      PROF(10, ct == PT, 19); STAMP(0);
      cluster_arrive();
      mbar_wait(gfull, 1);
      mbar_wait(gfull + 8, 1);
      bar_sync(2 + wg, 256);
      wg_fence();
      HALF_STAGE(o, 7, 1);
      HALF_STAGE(o, 8, 3);
      wg_commit();
      STAMP(16);
      mbar_wait(gfull + 16, 1);
      STAMP(17);
      wg_fence();
      HALF_STAGE(o, 6, 11);
      wg_commit();
      bar_arrive(3 - wg, 256);
      mbar_wait(bar_par, 0);
      uint32_t* xo = g_xch + ((size_t)b * 8 * 256 + ct) * 4;
      const uint32_t* xi = g_xch + ((size_t)(b ^ 2) * 8 * 256 + ct) * 4;
      const uint32_t par1 = (~lds1(par + PAR_CONST + 4) & 1) << 16;
      wg_wait<1>();
      mbar_arrive_pred(bar_rel, lane0);
      wg_wait<0>();
      keep(o);
      mbar_arrive_pred(bar_ring, lane0);
      PROF(8, ct == PT, 20); STAMP(1);
#define SEND(i) st_b128(xo + (i) * 1024, (pack_bf(o[8 * (i)], o[8 * (i) + 1]) & ~0x10000u) | par1, pack_bf(o[8 * (i) + 2], o[8 * (i) + 3]), \
                        pack_bf(o[8 * (i) + 4], o[8 * (i) + 5]), pack_bf(o[8 * (i) + 6], o[8 * (i) + 7]))
#pragma unroll
      for (int i = 0; i < NS1; i++) SEND(i);
      PROF(8, ct == PT, 21); STAMP(2);
      bar_sync(2 + wg, 256);
      wg_fence();
      HALF_STAGE(s, 7, 0);
      HALF_STAGE(s, 8, 2);
      HALF_STAGE(s, 6, 10);
      wg_commit();
      bar_arrive(3 - wg, 256);
      STAMP(18);
      mbar_wait(gfull + 24, 1);
#pragma unroll
      for (int i = NS1; i < 8; i++) SEND(i);
      uint4 v[8];
      STAMP(19);
      mbar_wait(bar_xres, 0);
      wg_wait<0>();
      mbar_arrive_pred(bar_ring + 8, lane0);
      bar_sync(2 + wg, 256);
      STAMP(20);
#pragma unroll
      for (int i = 0; i < LD2; i++) v[i] = ld_b128(xi + i * 1024);
      mbar_wait(bar_xres, 0);
      wg_fence();
      HALF_STAGE(s, 9, 4);
      wg_commit();
      mbar_wait(bar_rx, 0);
      wg_fence();
      HALF_STAGE(s, 1, 5);
      wg_commit();
      bar_arrive(3 - wg, 256);
      STAMP(21);
#pragma unroll
      for (int i = LD2; i < 8; i++) v[i] = ld_b128(xi + i * 1024);
      mbar_wait(bar_xres, 0);
      wg_wait<0>();
      keep(s);
      mbar_arrive_pred(bar_ring + 16, lane0);
      PROF(10, ct == PT, 23); STAMP(4);
#pragma unroll
      for (int i = 0; i < 16; i += 2) ldmatrix4((trow ^ ((i & 7) << 4)) + (i >> 3) * 16384, xr[2 * i], xr[2 * i + 1], xr[2 * i + 2], xr[2 * i + 3]);
      uint32_t ga[16];
      uint4 bw[8];
#pragma unroll
      for (int i = 0; i < 8; i++) {
        if (!(i & 1)) {
          const uint4 t = lds4(par + PAR_SINK + i * 32 + tq * 16);
          ga[2 * i] = t.x; ga[2 * i + 1] = t.y; ga[2 * i + 2] = t.z; ga[2 * i + 3] = t.w;
        }
        bw[i] = lds4(par + PAR_T1 + i * 64 + tq * 16);
        if (!(g & 1)) { bw[i].x = 0x3f803f80u; bw[i].y = 0x3f803f80u; }
      }
      uint32_t pk[32];
      pack_p(s, pk);
      keep(pk);
      {
        uint32_t n = 0, miss;
        do {
          miss = 0;
#pragma unroll
          for (int i = 0; i < 8; i++) miss |= v[i].x ^ par1;
          miss = __any_sync(0xffffffffu, miss & 0x10000u);
          if (miss) {
#pragma unroll
            for (int i = 0; i < 8; i++)
              asm volatile("{ .reg .pred p; .reg .b32 t; xor.b32 t, %0, %5; and.b32 t, t, 0x10000; setp.ne.u32 p, t, 0;\n"
                           "@p ld.relaxed.gpu.global.v4.u32 {%0, %1, %2, %3}, [%4]; }"
                           : "+r"(v[i].x), "+r"(v[i].y), "+r"(v[i].z), "+r"(v[i].w) : "l"(xi + i * 1024), "r"(par1) : "memory");
          }
          watchdog(n);
        } while (miss);
      }
      PROF(8, ct == PT, 22); STAMP(3);
      float ds[4] = {0.f, 0.f, 0.f, 0.f}, dl[4] = {0.f, 0.f, 0.f, 0.f}, q0[4] = {0.f, 0.f, 0.f, 0.f}, q1[4] = {0.f, 0.f, 0.f, 0.f};
#pragma unroll
      for (int i = 0; i < 8; i++) {
        const uint32_t u0 = hfma2(ga[2 * i], hadd2(pk[4 * i], v[i].x & ~0x10000u), xr[4 * i]);
        const uint32_t u1 = hfma2(ga[2 * i], hadd2(pk[4 * i + 1], v[i].y), xr[4 * i + 1]);
        const uint32_t u2 = hfma2(ga[2 * i + 1], hadd2(pk[4 * i + 2], v[i].z), xr[4 * i + 2]);
        const uint32_t u3 = hfma2(ga[2 * i + 1], hadd2(pk[4 * i + 3], v[i].w), xr[4 * i + 3]);
        xr[4 * i] = u0; xr[4 * i + 1] = u1; xr[4 * i + 2] = u2; xr[4 * i + 3] = u3;
        mma16816(ds, u0, u1, u2, u3, bw[i].x, bw[i].y);
        mma16816(dl, u0, u1, u2, u3, bw[i].z, bw[i].w);
        mma16816(q0, u0, u1, u2, u3, u0, u2);
        mma16816(q1, u0, u1, u2, u3, u1, u3);
      }
      const float sqa = __shfl_sync(0xffffffffu, (g & 1) ? q0[1] : q0[0], g * 4 + (g >> 1));
      const float sqb = __shfl_sync(0xffffffffu, (g & 1) ? q1[3] : q1[2], g * 4 + (g >> 1));
      own = (tq & 1) ? make_uint4(__float_as_uint(ds[2]), __float_as_uint(sqb), __float_as_uint(ds[3] + dl[3]), tag)
                                 : make_uint4(__float_as_uint(ds[0]), __float_as_uint(sqa), __float_as_uint(ds[1] + dl[1]), tag);
      if (tq < 2) st_b128(sp[0], own.x, own.y, own.z, own.w);
#pragma unroll
      for (int k = 0; k < 4; k++) sv[k] = make_uint4(0, 0, 0, 0);
    }
    PROF(8, ct == PT, 29); STAMP(5);
    uint32_t mm, ih, il;
    float rbest;
    uint32_t wf[128];
    const uint32_t frow = (ln & 7) + (ln >> 4) * 8;
    const uint32_t wfo = base + (warp & 1) * 8192 + frow * 64 + ((((ln >> 3) & 1) ^ ((frow >> 1) & 3)) << 4);
#define LOAD_WF(m) _Pragma("unroll") for (int f = 0; f < 16; f++) {                                                   \
      const int r = ((f >> 1) * 4 + (m) * 2 + (f & 1)) * 4;                                                           \
      ldmatrix4t(((wfo + unit_of((m) ? FT_U : FT_G, warp >> 1)) ^ ((f & 1) * 32)) + (f >> 1) * 1024, wf[r], wf[r + 1], wf[r + 2], wf[r + 3]); \
    }
    bool early;
    {
#pragma unroll
      for (int i = 0; i < 16; i += 2) stmatrix4((trow ^ ((i & 7) << 4)) + (i >> 3) * 16384, xr[2 * i], xr[2 * i + 1], xr[2 * i + 2], xr[2 * i + 3]);
      const uint4 cst = lds4(par + PAR_CONST);
      const float A1 = __uint_as_float(cst.x), A2 = __uint_as_float(cst.z);
      uint32_t n = 0;
      early = false;
#pragma unroll 1
      while (true) {
        uint32_t miss;
        asm volatile("{ .reg .pred p0, p1, p2, p3; .reg .b64 u, v; .reg .b128 w;\n"
                     "setp.ge.u32 p0, %22, 2; setp.ne.and.u32 p0, %4, %21, p0; setp.ne.u32 p1, %8, %21; setp.ne.u32 p2, %12, %21; setp.ne.u32 p3, %16, %21;\n"
                     "@p0 ld.relaxed.gpu.global.v4.u32 {%1, %2, %3, %4}, [%17];\n"
                     "@p1 ld.relaxed.gpu.global.v4.u32 {%5, %6, %7, %8}, [%18];\n"
                     "@p2 ld.relaxed.gpu.global.v4.u32 {%9, %10, %11, %12}, [%19];\n"
                     "@p3 ld.relaxed.gpu.global.v4.u32 {%13, %14, %15, %16}, [%20];\n"
                     "or.pred p0, p0, p1; or.pred p2, p2, p3; or.pred p0, p0, p2; vote.sync.any.pred p0, p0, 0xffffffff; selp.u32 %0, 1, 0, p0; }"
                     : "=r"(miss), "+r"(sv[0].x), "+r"(sv[0].y), "+r"(sv[0].z), "+r"(sv[0].w), "+r"(sv[1].x), "+r"(sv[1].y), "+r"(sv[1].z), "+r"(sv[1].w),
                       "+r"(sv[2].x), "+r"(sv[2].y), "+r"(sv[2].z), "+r"(sv[2].w), "+r"(sv[3].x), "+r"(sv[3].y), "+r"(sv[3].z), "+r"(sv[3].w)
                     : "l"(sp[0]), "l"(sp[1]), "l"(sp[2]), "l"(sp[3]), "r"(tag), "r"(tq) : "memory");
        if (!miss) break;
        if (!early && (b >= NFFN || __all_sync(0xffffffffu, mbar_test(bar_box + (warp >> 1) * 8, 0)))) {
          early = true;
          LOAD_WF(0);
          __syncwarp();
          mbar_arrive_pred(bar_gate, lane0);
        }
        watchdog(n);
      }
      const uint4 v0 = tq < 2 ? own : sv[0], v1 = sv[1], v2 = sv[2], v3 = sv[3];
      PROF(8, ct == PT, 30); STAMP(6);
      float su = (__uint_as_float(v0.x) + __uint_as_float(v1.x)) + (__uint_as_float(v2.x) + __uint_as_float(v3.x));
      float sq = (__uint_as_float(v0.y) + __uint_as_float(v1.y)) + (__uint_as_float(v2.y) + __uint_as_float(v3.y));
      float dt = (__uint_as_float(v0.z) + __uint_as_float(v1.z)) + (__uint_as_float(v2.z) + __uint_as_float(v3.z));
      su += __shfl_xor_sync(0xffffffffu, su, 2); sq += __shfl_xor_sync(0xffffffffu, sq, 2); dt += __shfl_xor_sync(0xffffffffu, dt, 2);
      const float m = su * (1.f / DM);
      float mb, sd;
      ln_scalars(m, fmaxf(sq * (1.f / DM) - m * m, 0.f), mb, sd);
      const float inv = rcp(sd);
      rbest = (dt - mb * A1) * inv + A2;
      mm = pack_bf(mb, mb);
      ih = pack_bf(inv, inv);
      const float lo = inv - bf_lo(ih);
      il = pack_bf(lo, lo);
    }
    int ibest;
    {
      const uint32_t bits = __float_as_uint(rbest);
      const uint32_t key = (((int)bits < 0 ? ~bits : bits | 0x80000000u) & ~0x1ffu) | ((127 - lrow0 - (tq & 1) * 8) << 2) | tag;
      sts1(par + PAR_RED + warp * 4, __reduce_max_sync(0xffffffffu, key));
      PROF(8, ct == PT, 38); STAMP(7);
      bar_sync(1, 256);
      const uint4 ka = lds4(par + PAR_RED), kb = lds4(par + PAR_RED + 16);
      const uint32_t k2 = max(max(max(ka.x, ka.y), max(ka.z, ka.w)), max(max(kb.x, kb.y), max(kb.z, kb.w)));
      if (ct < CR && cj == 0) st_relaxed(g_cand + ct * 512 + rb * CS, k2);
      ibest = 127 - ((k2 >> 2) & 127);
    }
    PROF(8, ct == PT, 39); STAMP(8);
    if ((ibest >> 4) == warp) {
      const int src = (ibest & 7) * 4 + ((ibest >> 3) & 1), ch = g * 2;
      const uint32_t cm = __shfl_sync(0xffffffffu, mm, src), ch_ = __shfl_sync(0xffffffffu, ih, src), cl = __shfl_sync(0xffffffffu, il, src);
      const uint32_t xa = res + (ch >> 3) * 16384 + ibest * 128 + (((ch & 7) ^ (ibest & 7)) << 4) + tq * 4;
      const uint32_t x0 = lds1(xa), x1 = lds1(xa ^ 16);
      const uint2 p0 = lds2(par + PAR_T2 + ch * 64 + tq * 16), p1 = lds2(par + PAR_T2 + ch * 64 + 64 + tq * 16);
      uint32_t* dst = g_row + rb * 2 * DM + cj * 128 + ln * 4;
      st_pairs(dst, ln_mod(x0, cm, ch_, cl, p0.x, p0.y), ln_mod(x1, cm, ch_, cl, p1.x, p1.y), tag);
      st_pairs(dst + DM, x0, x1, tag);
      __syncwarp();
    }
    PROF(8, ct == PT, 37); STAMP(9);
    uint32_t wd[64];
    const uint32_t wda = base + unit_of(FT_D, warp >> 1) + (warp & 1) * 8192 + frow * 128 + ((((ln >> 3) & 1) ^ (ln & 7)) << 4);
#define LOAD_WD(f) ldmatrix4t((wda ^ ((((f) >> 1) & 3) * 32)) + ((f) >> 3) * 4096 + ((f) & 1) * 2048, wd[4 * (f)], wd[4 * (f) + 1], wd[4 * (f) + 2], wd[4 * (f) + 3])
    if (!early) {
      if (b < NFFN) mbar_wait(bar_box + (warp >> 1) * 8, 0);
      LOAD_WF(0);
      __syncwarp();
      mbar_arrive_pred(bar_gate, lane0);
    }
    if (b < NFFN) {
      const uint32_t own = base + unit_of(FT_G, warp >> 1) + (warp & 1) * 8192;
      mbar_wait(bar_box + (4 + (warp >> 1)) * 8, 0);
      LOAD_WF(1);
      uint32_t* const ydst = ypart_slot(b, warp * 16 + (tq & 1) * 8 + g);
      PROF(8, ct == PT, 31); STAMP(10);
      bool wdok;
      {
        uint32_t n = 0;
        while (!(wdok = __all_sync(0xffffffffu, mbar_test(bar_box + (8 + (warp >> 1)) * 8, 0))) && !__all_sync(0xffffffffu, mbar_test(bar_sel, 0))) watchdog(n);
      }
      if (wdok) {
#pragma unroll
        for (int f = 0; f < 16; f++) LOAD_WD(f);
      }
      STAMP(11);
      mbar_wait(bar_sel, 0);
      PROF(8, ct == PT, 33); STAMP(12);
      float d[8][4];
#pragma unroll
      for (int i = 0; i < 4; i++) { d[i][0] = 0.f; d[i][1] = 0.f; d[i][2] = 0.f; d[i][3] = 0.f; }
#pragma unroll
      for (int ks = 0; ks < 8; ks++) {
        const uint2 hb = lds2(own + 256 + ks * 32 + tq * 8);
#pragma unroll
        for (int mt = 0; mt < 4; mt++) {
          const int r = ks * 16 + mt * 4;
          mma16816(d[mt], wf[r], wf[r + 1], wf[r + 2], wf[r + 3], hb.x, hb.y);
        }
      }
      sts2(own + (tq * 8 + g) * 8, __float_as_uint((tq & 2) ? ((tq & 1) ? d[1][2] : d[1][0]) : ((tq & 1) ? d[0][2] : d[0][0])),
           __float_as_uint((tq & 2) ? ((tq & 1) ? d[3][2] : d[3][0]) : ((tq & 1) ? d[2][2] : d[2][0])));
      bar_sync(1, 256);
      uint32_t ab[4];
      {
        float G = 0.f, U = 0.f;
        uint2 pv[8];
#pragma unroll
        for (int w8 = 0; w8 < 8; w8++) pv[w8] = lds2(base + ln * 8 + ((FT_G >> (w8 >> 1) * 4) & 15) * UNIT + (w8 & 1) * 8192);
#pragma unroll
        for (int w8 = 0; w8 < 8; w8 += 2) {
          G += __uint_as_float(pv[w8].x) + __uint_as_float(pv[w8 + 1].x);
          U += __uint_as_float(pv[w8].y) + __uint_as_float(pv[w8 + 1].y);
        }
        const float act = rbf(silu_f(rbf(G))) * rbf(U);
        const uint32_t pk = pack_bf(act, __shfl_down_sync(0xffffffffu, act, 1));
#pragma unroll
        for (int i = 0; i < 4; i++) ab[i] = __shfl_sync(0xffffffffu, pk, i * 8 + tq * 2);
      }
      if (!wdok) {
        mbar_wait(bar_box + (8 + (warp >> 1)) * 8, 0);
#pragma unroll
        for (int f = 0; f < 16; f++) LOAD_WD(f);
      }
      PROF(8, ct == PT, 34); STAMP(13);
#pragma unroll
      for (int mt = 0; mt < 8; mt++) {
        d[mt][0] = 0.f; d[mt][1] = 0.f; d[mt][2] = 0.f; d[mt][3] = 0.f;
        mma16816(d[mt], wd[mt * 8], wd[mt * 8 + 1], wd[mt * 8 + 2], wd[mt * 8 + 3], ab[0], ab[1]);
        mma16816(d[mt], wd[mt * 8 + 4], wd[mt * 8 + 5], wd[mt * 8 + 6], wd[mt * 8 + 7], ab[2], ab[3]);
      }
      uint32_t yw[4];
#pragma unroll
      for (int i = 0; i < 4; i++) yw[i] = (tq & 1) ? pack_bf(d[2 * i][2], d[2 * i + 1][2]) : pack_bf(d[2 * i][0], d[2 * i + 1][0]);
      if (tq < 2) st_b128(ydst, (yw[0] & ~1u) | (tag & 1), (yw[1] & ~1u) | (tag >> 1), yw[2], yw[3]);
      PROF(8, ct == PT, 35); STAMP(14);
    }
    mbar_wait(bar_sel, 0);
    mbar_arrive_pred(bar_win, ct == 0);
    const int iwin = lds1(par + PAR_CONST + 60) & 0x7ff;
    const bool cand = (iwin >> 4) == rb * 8 + warp;
    {
      const uint32_t mm0 = __shfl_sync(0xffffffffu, mm, ln & ~1), mm1 = __shfl_sync(0xffffffffu, mm, ln | 1);
      const uint32_t ih0 = __shfl_sync(0xffffffffu, ih, ln & ~1), ih1 = __shfl_sync(0xffffffffu, ih, ln | 1);
      const uint32_t il0 = __shfl_sync(0xffffffffu, il, ln & ~1), il1 = __shfl_sync(0xffffffffu, il, ln | 1);
#pragma unroll 1
      for (int hf = 0; hf < 2; hf++) {
        uint32_t x[16];
#pragma unroll
        for (int i = 0; i < 8; i += 2) ldmatrix4((trow ^ (i << 4)) + hf * 16384, x[2 * i], x[2 * i + 1], x[2 * i + 2], x[2 * i + 3]);
#pragma unroll
        for (int i = 0; i < 8; i++) {
          const uint4 pv = lds4(par + PAR_T2 + (hf * 8 + i) * 64 + tq * 16);
          x[2 * i] = hfma2(hfma2(ln_norm(x[2 * i], mm0, ih0, il0), pv.x, pv.y), pv.z, x[2 * i]);
          x[2 * i + 1] = hfma2(hfma2(ln_norm(x[2 * i + 1], mm1, ih1, il1), pv.x, pv.y), pv.z, x[2 * i + 1]);
        }
#pragma unroll
        for (int i = 0; i < 8; i += 2) stmatrix4((trow ^ (i << 4)) + hf * 16384, x[2 * i], x[2 * i + 1], x[2 * i + 2], x[2 * i + 3]);
        if (!cand) fence_async_smem();
        __syncwarp();
        if (!cand && elect_one()) {
          tma2d_store(&maps.out, res + hf * 16384 + warp * 2048, cj * 128 + hf * 64, rb * 128 + warp * 16);
          asm volatile("cp.async.bulk.commit_group;" ::: "memory");
        }
      }
    }
    if (cand) {
      const int wrow0 = warp * 16;
#pragma unroll 2
      for (int p = 0; p < 8; p++) {
        const int row = 2 * p + (ln >> 4), ch = ln & 15;
        const uint4 v = lds4(res + (ch >> 3) * 16384 + (wrow0 + row) * 128 + (((ch & 7) ^ (row & 7)) << 4));
        if (rb * 128 + wrow0 + row != iwin) *reinterpret_cast<uint4*>(P.out + (size_t)(rb * 128 + wrow0 + row) * DM + cj * 128 + ch * 8) = v;
      }
    }
    asm volatile("cp.async.bulk.wait_group.read 0;" ::: "memory");
    PROF(8, ct == PT, 11); STAMP(15);
    cluster_wait();
  }
}

typedef CUresult (*EncodeFn)(CUtensorMap*, CUtensorMapDataType, cuuint32_t, void*, const cuuint64_t*, const cuuint64_t*,
                             const cuuint32_t*, const cuuint32_t*, CUtensorMapInterleave, CUtensorMapSwizzle,
                             CUtensorMapL2promotion, CUtensorMapFloatOOBfill);

void map2d(EncodeFn enc, CUtensorMap* m, const void* p, uint64_t rows, uint64_t cols, uint32_t brows) {
  cuuint64_t dims[2] = {cols, rows}, strides[1] = {cols * 2};
  cuuint32_t box[2] = {64, brows}, es[2] = {1, 1};
  enc(m, CU_TENSOR_MAP_DATA_TYPE_BFLOAT16, 2, const_cast<void*>(p), dims, strides, box, es, CU_TENSOR_MAP_INTERLEAVE_NONE,
      CU_TENSOR_MAP_SWIZZLE_128B, CU_TENSOR_MAP_L2_PROMOTION_L2_256B, CU_TENSOR_MAP_FLOAT_OOB_FILL_NONE);
}
void map2d_narrow(EncodeFn enc, CUtensorMap* m, const void* p, uint64_t rows, uint64_t cols, uint32_t brows) {
  cuuint64_t dims[2] = {cols, rows}, strides[1] = {cols * 2};
  cuuint32_t box[2] = {32, brows}, es[2] = {1, 1};
  enc(m, CU_TENSOR_MAP_DATA_TYPE_BFLOAT16, 2, const_cast<void*>(p), dims, strides, box, es, CU_TENSOR_MAP_INTERLEAVE_NONE,
      CU_TENSOR_MAP_SWIZZLE_64B, CU_TENSOR_MAP_L2_PROMOTION_L2_64B, CU_TENSOR_MAP_FLOAT_OOB_FILL_NONE);
}
void map3d(EncodeFn enc, CUtensorMap* m, const void* p, uint64_t rows, uint64_t cols, uint32_t brows, uint32_t nch) {
  cuuint64_t dims[3] = {64, rows, cols / 64}, strides[2] = {cols * 2, 128};
  cuuint32_t box[3] = {64, brows, nch}, es[3] = {1, 1, 1};
  enc(m, CU_TENSOR_MAP_DATA_TYPE_BFLOAT16, 3, const_cast<void*>(p), dims, strides, box, es, CU_TENSOR_MAP_INTERLEAVE_NONE,
      CU_TENSOR_MAP_SWIZZLE_128B, CU_TENSOR_MAP_L2_PROMOTION_L2_256B, CU_TENSOR_MAP_FLOAT_OOB_FILL_NONE);
}

}

extern "C" void kernel_launch(void* const* d_in, const int* in_sizes, int n_in, void* d_out, int out_size) {
  (void)in_sizes; (void)n_in; (void)out_size;
  static EncodeFn enc = nullptr;
  if (!enc) {
    void* fn = nullptr;
    cudaDriverEntryPointQueryResult st;
    cudaGetDriverEntryPoint("cuTensorMapEncodeTiled", &fn, cudaEnableDefault, &st);
    enc = (EncodeFn)fn;
    cudaFuncSetAttribute(fused_kernel, cudaFuncAttributeMaxDynamicSharedMemorySize, SMEM_BYTES);
  }
  Maps maps;
  map2d(enc, &maps.x, d_in[0], SEQ, DM, 128);
  map2d(enc, &maps.out, d_out, SEQ, DM, 16);
  map3d(enc, &maps.wq, d_in[3], DM, NQ, 64, 2);
  map3d(enc, &maps.k, d_in[1], 4 * SK, 128, 128, 1);
  map3d(enc, &maps.v, d_in[2], 4 * SK, 128, 128, 1);
  map3d(enc, &maps.wo, d_in[4], NQ, DM, 64, 2);
  map2d_narrow(enc, &maps.wg, d_in[7], DM, FF, 256);
  map2d_narrow(enc, &maps.wu, d_in[8], DM, FF, 256);
  map3d(enc, &maps.wd, d_in[9], FF, DM, 32, 4);
  map2d_narrow(enc, &maps.wm, d_in[11], DM, NMOD, 256);
  Ptrs p;
  p.x = (const __nv_bfloat16*)d_in[0];
  p.w_r = (const __nv_bfloat16*)d_in[6];
  p.w_gate = (const __nv_bfloat16*)d_in[7];
  p.w_up = (const __nv_bfloat16*)d_in[8];
  p.w_down = (const __nv_bfloat16*)d_in[9];
  p.c = (const __nv_bfloat16*)d_in[10];
  p.w_mod = (const __nv_bfloat16*)d_in[11];
  p.out = (__nv_bfloat16*)d_out;
  fused_kernel<<<NMAIN + NHELP, 384, SMEM_BYTES>>>(maps, p);
}
```

```cpp
#include <cuda_runtime.h>
#include <cuda_bf16.h>
#include <cuda.h>
#include <stdint.h>
#include <type_traits>

#define HD 2
#define HDX 2
#define NRS 8
#define OSL 900
#define OSL2 400
#define RSL 40
#define VREL 5
#define OPS 8192
#define ODS1 5
#define ODS 7
#define PG0 15
#define WB 2
#define WN 20
#define HU 32
#define RES0 17
#define RES1 20
#define GOST 20
#define NS1 5
#define LD2 4
#define FPACE0 2
#define FPACE 3
#define CR 8
#define CS 8

namespace {

constexpr int SEQ = 2048, DM = 1024, NQ = 4096, SK = 2048, WIN = 512, FF = 3584, NMOD = 6144;
constexpr int NMAIN = 128, NHELP = 4, NFFN = 112;
constexpr int NSLOT = 4, SLOT_BYTES = 32768, UNIT = 16384, GST_BYTES = 3 * UNIT;
constexpr uint32_t XT1 = 0xDCBA, XT2 = 0x9687;
constexpr uint32_t WT0 = 0xA741, WT1 = 0x7420, WT2 = 0x4A20;
constexpr uint32_t AT0 = WT1, AT1 = WT2;
constexpr uint32_t QT = 0xDC9696DC;
constexpr int OFF_STAGE = 12 * UNIT;
constexpr uint32_t FT_G = 0x07B3, FT_U = 0xA628, FT_D = 0x5149;
constexpr int OFF_RES = 12 * UNIT;
constexpr int OFF_PAR = 14 * UNIT;
constexpr int OFF_BAR = OFF_PAR + 2528;
constexpr int SMEM_BYTES = OFF_BAR + 544;
static_assert(SMEM_BYTES <= 232448, "smem");

constexpr int PAR_T1 = 0;
constexpr int PAR_T2 = 512;
constexpr int PAR_CONST = 1536;
constexpr int PAR_RED = 1600;
constexpr int PAR_SINK = 2176;

struct Maps {
  CUtensorMap x, wq, k, v, wo, wg, wu, wd, wm, out;
};
struct Ptrs {
  const __nv_bfloat16 *x, *w_r, *c, *w_mod, *w_gate, *w_up, *w_down;
  __nv_bfloat16* out;
};

__device__ __align__(1024) uint8_t g_act[16 * 80 * UNIT];
__device__ __align__(128) uint32_t g_mod[NMOD];
__device__ __align__(128) uint32_t g_modp[2 * 2 * DM];
__device__ __align__(128) uint32_t g_ln1[SEQ * 4];
__device__ __align__(128) uint32_t g_cnt_h[16 * 32];
__device__ __align__(128) uint32_t g_cnt_o[128 * 32];
__device__ __align__(128) uint32_t g_xch[NMAIN * 8 * 256 * 4];
__device__ __align__(128) uint32_t g_stats[8 * SEQ * 4];
__device__ __align__(128) uint32_t g_cand[CR * 512];
__device__ __align__(128) uint32_t g_row[16 * 2 * DM];
__device__ __align__(128) uint32_t g_ypart[NMAIN * NFFN * 4];
__device__ __forceinline__ uint32_t* ypart_slot(int writer, int reader) { return g_ypart + (writer * NMAIN + reader) * 4; }
__device__ uint32_t g_epoch;

__device__ __forceinline__ uint32_t fresh_lane() { uint32_t l; asm volatile("mov.u32 %0, %%laneid;" : "=r"(l)); return l; }
__device__ __forceinline__ uint32_t frag_offset(int warp) {
  const uint32_t l = fresh_lane();
  return ((warp & 3) * 16 + (l & 15)) * 128 + (((l >> 4) ^ (l & 7)) << 4);
}
__device__ __forceinline__ bool elect_one() {
  uint32_t p;
  asm volatile("{ .reg .pred q; elect.sync _|q, 0xffffffff; selp.u32 %0, 1, 0, q; }" : "=r"(p));
  return p;
}
__device__ __forceinline__ uint32_t smem_u32(const void* p) { return (uint32_t)__cvta_generic_to_shared(p); }
__device__ __forceinline__ void mbar_init(uint32_t bar, uint32_t cnt) {
  asm volatile("mbarrier.init.shared::cta.b64 [%0], %1;" ::"r"(bar), "r"(cnt) : "memory");
}
__device__ __forceinline__ void mbar_expect_tx(uint32_t bar, uint32_t bytes) {
  asm volatile("mbarrier.arrive.expect_tx.shared::cta.b64 _, [%0], %1;" ::"r"(bar), "r"(bytes) : "memory");
}
__device__ __forceinline__ void mbar_arrive(uint32_t bar) {
  asm volatile("mbarrier.arrive.shared::cta.b64 _, [%0];" ::"r"(bar) : "memory");
}
__device__ __forceinline__ void mbar_arrive_pred(uint32_t bar, bool p) {
  asm volatile("{ .reg .pred p; setp.ne.b32 p, %1, 0; @p mbarrier.arrive.shared::cta.b64 _, [%0]; }" ::"r"(bar), "r"((int)p) : "memory");
}
__device__ __forceinline__ void mbar_arrive_cl(uint32_t bar, uint32_t off, bool p = true) {
  asm volatile("{ .reg .pred p, q; .reg .b32 a; setp.ne.b32 q, %2, 0; setp.ne.and.b32 p, %0, 0, q; add.u32 a, %0, %1; @p mbarrier.arrive.shared::cluster.b64 _, [a]; }"
               ::"r"(bar), "r"(off), "r"((int)p) : "memory");
}
__device__ __forceinline__ uint32_t mapa(uint32_t addr, uint32_t cta) {
  uint32_t r; asm("mapa.shared::cluster.u32 %0, %1, %2;" : "=r"(r) : "r"(addr), "r"(cta)); return r;
}
__device__ __forceinline__ void cluster_arrive() { asm volatile("barrier.cluster.arrive.relaxed.aligned;" ::: "memory"); }
__device__ __forceinline__ void cluster_wait() { asm volatile("barrier.cluster.wait.aligned;" ::: "memory"); }
__device__ __forceinline__ void watchdog(uint32_t& n) {
}
__device__ __forceinline__ void mbar_wait(uint32_t bar, uint32_t parity) {
  asm volatile("{\n.reg .pred p;\nWAIT_%=:\nmbarrier.try_wait.parity.shared::cta.b64 p, [%0], %1;\n@!p bra WAIT_%=;\n}" ::"r"(bar), "r"(parity) : "memory");
}
__device__ __forceinline__ bool mbar_test(uint32_t bar, uint32_t parity) {
  uint32_t ok;
  asm volatile("{\n.reg .pred p;\nmbarrier.test_wait.parity.shared::cta.b64 p, [%1], %2;\nselp.u32 %0, 1, 0, p;\n}" : "=r"(ok) : "r"(bar), "r"(parity) : "memory");
  return ok;
}
__device__ __forceinline__ uint64_t l2_stream() {
  uint64_t f; asm("createpolicy.fractional.L2::evict_first.b64 %0, 1.0;" : "=l"(f)); return f;
}
__device__ __forceinline__ uint64_t l2_normal() {
  uint64_t f; asm("createpolicy.fractional.L2::evict_normal.b64 %0, 1.0;" : "=l"(f)); return f;
}
__device__ __forceinline__ void tma2d(uint32_t dst, const CUtensorMap* m, int c0, int c1, uint32_t bar) {
  asm volatile("cp.async.bulk.tensor.2d.shared::cluster.global.mbarrier::complete_tx::bytes.L2::cache_hint [%0], [%1, {%3, %4}], [%2], %5;"
               ::"r"(dst), "l"(m), "r"(bar), "r"(c0), "r"(c1), "l"(l2_stream()) : "memory");
}
__device__ __forceinline__ void bulk_load(uint32_t dst, const void* src, uint32_t bytes, uint32_t bar) {
  asm volatile("cp.async.bulk.shared::cluster.global.mbarrier::complete_tx::bytes [%0], [%1], %2, [%3];" ::"r"(dst), "l"(src), "r"(bytes), "r"(bar) : "memory");
}
__device__ __forceinline__ void bulk_load_stream(uint32_t dst, const void* src, uint32_t bytes, uint32_t bar, uint64_t pol = l2_stream()) {
  asm volatile("cp.async.bulk.shared::cluster.global.mbarrier::complete_tx::bytes.L2::cache_hint [%0], [%1], %2, [%3], %4;"
               ::"r"(dst), "l"(src), "r"(bytes), "r"(bar), "l"(pol) : "memory");
}
__device__ __forceinline__ void tma2d_store(const CUtensorMap* m, uint32_t src, int c0, int c1) {
  asm volatile("cp.async.bulk.tensor.2d.global.shared::cta.bulk_group [%0, {%2, %3}], [%1];" ::"l"(m), "r"(src), "r"(c0), "r"(c1) : "memory");
}
__device__ __forceinline__ void bulk_store(void* dst, uint32_t src, uint32_t bytes) {
  asm volatile("cp.async.bulk.global.shared::cta.bulk_group [%0], [%1], %2;" ::"l"(dst), "r"(src), "r"(bytes) : "memory");
}
__device__ __forceinline__ int slice_of(int i) { return i + ((i & 7) == 1) - ((i & 7) == 2); }
__device__ __forceinline__ uint32_t unit_of(uint32_t table, uint32_t i) { return ((table >> (i * 4)) & 15) * UNIT; }
__device__ __forceinline__ void tma3d(uint32_t dst, const CUtensorMap* m, int c0, int c1, int c2, uint32_t bar) {
  asm volatile("cp.async.bulk.tensor.3d.shared::cluster.global.mbarrier::complete_tx::bytes.L2::cache_hint [%0], [%1, {%3, %4, %5}], [%2], %6;"
               ::"r"(dst), "l"(m), "r"(bar), "r"(c0), "r"(c1), "r"(c2), "l"(l2_stream()) : "memory");
}
template <bool STREAM>
__device__ __forceinline__ void tma3d_mc(uint32_t dst, const CUtensorMap* m, int c0, int c1, int c2, uint32_t bar) {
  if (STREAM)
    asm volatile("cp.async.bulk.tensor.3d.shared::cluster.global.mbarrier::complete_tx::bytes.multicast::cluster.L2::cache_hint [%0], [%1, {%3, %4, %5}], [%2], %6, %7;"
                 ::"r"(dst), "l"(m), "r"(bar), "r"(c0), "r"(c1), "r"(c2), "h"((uint16_t)3), "l"(l2_stream()) : "memory");
  else
    asm volatile("cp.async.bulk.tensor.3d.shared::cluster.global.mbarrier::complete_tx::bytes.multicast::cluster [%0], [%1, {%3, %4, %5}], [%2], %6;"
                 ::"r"(dst), "l"(m), "r"(bar), "r"(c0), "r"(c1), "r"(c2), "h"((uint16_t)3) : "memory");
}
__device__ __forceinline__ void prefetch_map(const CUtensorMap* m) {
  asm volatile("prefetch.tensormap [%0];" ::"l"(m) : "memory");
}
__device__ __forceinline__ void fence_async() { asm volatile("fence.proxy.async.global;" ::: "memory"); }
__device__ __forceinline__ void fence_async_smem() { asm volatile("fence.proxy.async.shared::cta;" ::: "memory"); }
__device__ __forceinline__ void bar_sync(int id, int n) { asm volatile("bar.sync %0, %1;" ::"r"(id), "r"(n) : "memory"); }
__device__ __forceinline__ void bar_arrive(int id, int n) { asm volatile("bar.arrive %0, %1;" ::"r"(id), "r"(n) : "memory"); }
__device__ __forceinline__ void wg_fence() { asm volatile("wgmma.fence.sync.aligned;" ::: "memory"); }
__device__ __forceinline__ void wg_commit() { asm volatile("wgmma.commit_group.sync.aligned;" ::: "memory"); }
template <int N> __device__ __forceinline__ void wg_wait() { asm volatile("wgmma.wait_group.sync.aligned %0;" ::"n"(N) : "memory"); }
__device__ __forceinline__ uint64_t make_desc(uint32_t addr, uint32_t lbo, uint32_t sbo) {
  return (uint64_t)((addr & 0x3FFFF) >> 4) | ((uint64_t)(lbo >> 4) << 16) | ((uint64_t)(sbo >> 4) << 32) | (1ull << 62);
}
__device__ __forceinline__ uint32_t ld_relaxed(const uint32_t* p) {
  uint32_t v; asm volatile("ld.relaxed.gpu.global.u32 %0, [%1];" : "=r"(v) : "l"(p) : "memory"); return v;
}
__device__ __forceinline__ uint32_t ld_acquire(const uint32_t* p) {
  uint32_t v; asm volatile("ld.acquire.gpu.global.u32 %0, [%1];" : "=r"(v) : "l"(p) : "memory"); return v;
}
__device__ __forceinline__ uint4 ld_relaxed4(const uint32_t* p) {
  uint4 v; asm volatile("ld.relaxed.gpu.global.v4.u32 {%0,%1,%2,%3}, [%4];" : "=r"(v.x), "=r"(v.y), "=r"(v.z), "=r"(v.w) : "l"(p) : "memory"); return v;
}
__device__ __forceinline__ void st_relaxed(uint32_t* p, uint32_t v) {
  asm volatile("st.relaxed.gpu.global.u32 [%0], %1;" ::"l"(p), "r"(v) : "memory");
}
__device__ __forceinline__ void st_relaxed4(uint32_t* p, uint32_t a, uint32_t b, uint32_t c, uint32_t d) {
  asm volatile("st.relaxed.gpu.global.v4.u32 [%0], {%1,%2,%3,%4};" ::"l"(p), "r"(a), "r"(b), "r"(c), "r"(d) : "memory");
}
__device__ __forceinline__ void st_b128(uint32_t* p, uint32_t a, uint32_t b, uint32_t c, uint32_t d) {
  asm volatile("{ .reg .b64 u, v; .reg .b128 w; mov.b64 u, {%1, %2}; mov.b64 v, {%3, %4}; mov.b128 w, {u, v}; st.relaxed.gpu.global.b128 [%0], w; }"
               ::"l"(p), "r"(a), "r"(b), "r"(c), "r"(d) : "memory");
}
__device__ __forceinline__ uint4 ld_b128(const uint32_t* p) {
  uint4 r;
  asm volatile("{ .reg .b64 u, v; .reg .b128 w; ld.relaxed.gpu.global.b128 w, [%4]; mov.b128 {u, v}, w; mov.b64 {%0, %1}, u; mov.b64 {%2, %3}, v; }"
               : "=r"(r.x), "=r"(r.y), "=r"(r.z), "=r"(r.w) : "l"(p) : "memory");
  return r;
}
__device__ __forceinline__ void st_pairs(uint32_t* p, uint32_t a, uint32_t b, uint32_t tag) {
  asm volatile("{ .reg .b64 u, v; mov.b64 u, {%1, %3}; mov.b64 v, {%2, %3}; st.relaxed.gpu.global.v2.b64 [%0], {u, v}; }"
               ::"l"(p), "r"(a), "r"(b), "r"(tag) : "memory");
}
__device__ __forceinline__ uint4 ld_pairs(const uint32_t* p) {
  uint4 v;
  asm volatile("{ .reg .b64 u, v; ld.relaxed.gpu.global.v2.b64 {u, v}, [%4]; mov.b64 {%0, %1}, u; mov.b64 {%2, %3}, v; }"
               : "=r"(v.x), "=r"(v.y), "=r"(v.z), "=r"(v.w) : "l"(p) : "memory");
  return v;
}
__device__ __forceinline__ uint2 ld_pair(const uint32_t* p) {
  uint2 v;
  asm volatile("{ .reg .b64 u; ld.relaxed.gpu.global.b64 u, [%2]; mov.b64 {%0, %1}, u; }" : "=r"(v.x), "=r"(v.y) : "l"(p) : "memory");
  return v;
}
__device__ __forceinline__ void red_release(uint32_t* p, uint32_t v) {
  asm volatile("red.release.gpu.global.add.u32 [%0], %1;" ::"l"(p), "r"(v) : "memory");
}
__device__ __forceinline__ uint32_t ldg_nc1(const void* p) {
  uint32_t v;
  asm volatile("ld.global.nc.u32 %0, [%1];" : "=r"(v) : "l"(p));
  return v;
}
__device__ __forceinline__ uint4 ldg_nc4(const void* p) {
  uint4 v; asm volatile("ld.global.nc.L1::no_allocate.v4.u32 {%0,%1,%2,%3}, [%4];" : "=r"(v.x), "=r"(v.y), "=r"(v.z), "=r"(v.w) : "l"(p)); return v;
}
__device__ __forceinline__ uint4 ldg_stream4(const void* p) {
  uint4 v;
  asm volatile("ld.global.nc.L1::no_allocate.L2::cache_hint.v4.u32 {%0,%1,%2,%3}, [%4], %5;" : "=r"(v.x), "=r"(v.y), "=r"(v.z), "=r"(v.w) : "l"(p), "l"(l2_stream()));
  return v;
}
__device__ __forceinline__ void stg4(void* p, uint4 v) {
  asm volatile("st.global.v4.u32 [%0], {%1,%2,%3,%4};" ::"l"(p), "r"(v.x), "r"(v.y), "r"(v.z), "r"(v.w) : "memory");
}
__device__ __forceinline__ void wait_counter(const uint32_t* p, uint32_t target) {
  uint32_t n = 0;
  while (__any_sync(0xffffffffu, (int)(ld_acquire(p) - target) < 0)) { watchdog(n); }
}
__device__ __forceinline__ uint32_t tagf(float v, uint32_t tag) { return (__float_as_uint(v) & ~3u) | tag; }
__device__ __forceinline__ bool tag_ok(uint4 v, uint32_t tag) { return (((v.x ^ tag) | (v.y ^ tag) | (v.z ^ tag) | (v.w ^ tag)) & 3u) == 0; }
__device__ __forceinline__ float untag_sum(uint32_t a, uint32_t b) { return __uint_as_float(a & ~3u) + __uint_as_float(b & ~3u); }
__device__ __forceinline__ uint4 poll4(const uint32_t* p, uint32_t tag) {
  uint4 v = ld_relaxed4(p);
  uint32_t n = 0;
  while (!__all_sync(0xffffffffu, tag_ok(v, tag))) { v = ld_relaxed4(p); watchdog(n); }
  return v;
}
__device__ __forceinline__ float bf_lo(uint32_t v) { return __uint_as_float(v << 16); }
__device__ __forceinline__ float bf_hi(uint32_t v) { return __uint_as_float(v & 0xffff0000u); }
__device__ __forceinline__ uint32_t pack_bf(float lo, float hi) {
  uint32_t r; asm("cvt.rn.bf16x2.f32 %0, %1, %2;" : "=r"(r) : "f"(hi), "f"(lo)); return r;
}
__device__ __forceinline__ float rbf(float v) { return __uint_as_float(pack_bf(0.f, v) & 0xffff0000u); }
__device__ __forceinline__ uint32_t hmul2(uint32_t a, uint32_t b) {
  uint32_t r; asm("mul.rn.bf16x2 %0, %1, %2;" : "=r"(r) : "r"(a), "r"(b)); return r;
}
__device__ __forceinline__ uint32_t hadd2(uint32_t a, uint32_t b) {
  uint32_t r; asm("add.rn.bf16x2 %0, %1, %2;" : "=r"(r) : "r"(a), "r"(b)); return r;
}
__device__ __forceinline__ uint32_t hsub2(uint32_t a, uint32_t b) {
  uint32_t r; asm("sub.rn.bf16x2 %0, %1, %2;" : "=r"(r) : "r"(a), "r"(b)); return r;
}
__device__ __forceinline__ float rcp(float x) { float r; asm("rcp.approx.ftz.f32 %0, %1;" : "=f"(r) : "f"(x)); return r; }
__device__ __forceinline__ float ex2(float x) { float r; asm("ex2.approx.ftz.f32 %0, %1;" : "=f"(r) : "f"(x)); return r; }
__device__ __forceinline__ void stmatrix4(uint32_t addr, uint32_t a, uint32_t b, uint32_t c, uint32_t d) {
  asm volatile("stmatrix.sync.aligned.m8n8.x4.shared.b16 [%0], {%1,%2,%3,%4};" ::"r"(addr), "r"(a), "r"(b), "r"(c), "r"(d) : "memory");
}
__device__ __forceinline__ void ldmatrix4(uint32_t addr, uint32_t& a, uint32_t& b, uint32_t& c, uint32_t& d) {
  asm volatile("ldmatrix.sync.aligned.m8n8.x4.shared.b16 {%0,%1,%2,%3}, [%4];" : "=r"(a), "=r"(b), "=r"(c), "=r"(d) : "r"(addr) : "memory");
}
__device__ __forceinline__ void ldmatrix4t(uint32_t addr, uint32_t& a, uint32_t& b, uint32_t& c, uint32_t& d) {
  asm volatile("ldmatrix.sync.aligned.m8n8.x4.trans.shared.b16 {%0,%1,%2,%3}, [%4];" : "=r"(a), "=r"(b), "=r"(c), "=r"(d) : "r"(addr) : "memory");
}
__device__ __forceinline__ void mma16816(float (&d)[4], uint32_t a0, uint32_t a1, uint32_t a2, uint32_t a3, uint32_t b0, uint32_t b1) {
  asm volatile("mma.sync.aligned.m16n8k16.row.col.f32.bf16.bf16.f32 {%0,%1,%2,%3}, {%4,%5,%6,%7}, {%8,%9}, {%0,%1,%2,%3};"
               : "+f"(d[0]), "+f"(d[1]), "+f"(d[2]), "+f"(d[3]) : "r"(a0), "r"(a1), "r"(a2), "r"(a3), "r"(b0), "r"(b1));
}
__device__ __forceinline__ void sts1(uint32_t a, uint32_t v) { asm volatile("st.shared.u32 [%0], %1;" ::"r"(a), "r"(v) : "memory"); }
__device__ __forceinline__ uint4 lds4(uint32_t a) {
  uint4 v; asm volatile("ld.shared.v4.u32 {%0,%1,%2,%3}, [%4];" : "=r"(v.x), "=r"(v.y), "=r"(v.z), "=r"(v.w) : "r"(a) : "memory"); return v;
}
__device__ __forceinline__ uint2 lds2(uint32_t a) {
  uint2 v; asm volatile("ld.shared.v2.u32 {%0,%1}, [%2];" : "=r"(v.x), "=r"(v.y) : "r"(a) : "memory"); return v;
}
__device__ __forceinline__ uint32_t lds1(uint32_t a) {
  uint32_t v; asm volatile("ld.shared.u32 %0, [%1];" : "=r"(v) : "r"(a) : "memory"); return v;
}
__device__ __forceinline__ void sts2(uint32_t a, uint32_t x, uint32_t y) { asm volatile("st.shared.v2.u32 [%0], {%1,%2};" ::"r"(a), "r"(x), "r"(y) : "memory"); }
__device__ __forceinline__ void sts4(uint32_t a, uint4 v) {
  asm volatile("st.shared.v4.u32 [%0], {%1,%2,%3,%4};" ::"r"(a), "r"(v.x), "r"(v.y), "r"(v.z), "r"(v.w) : "memory");
}
__device__ __forceinline__ float silu_f(float v) { return __fdividef(v, 1.f + __expf(-v)); }
__device__ __forceinline__ uint32_t hfma2(uint32_t a, uint32_t b, uint32_t c) {
  uint32_t r; asm("fma.rn.bf16x2 %0, %1, %2, %3;" : "=r"(r) : "r"(a), "r"(b), "r"(c)); return r;
}
__device__ __forceinline__ void split_inv(float sd, uint32_t& ih, uint32_t& il) {
  const float inv = rcp(sd);
  ih = pack_bf(inv, inv);
  const float lo = inv - bf_lo(ih);
  il = pack_bf(lo, lo);
}
__device__ __forceinline__ uint32_t ln_norm(uint32_t x, uint32_t mean2, uint32_t ih, uint32_t il) {
  const uint32_t d = hsub2(x, mean2);
  return hfma2(d, ih, hmul2(d, il));
}
__device__ __forceinline__ uint32_t ln_mod(uint32_t x, uint32_t mean2, uint32_t ih, uint32_t il, uint32_t c1, uint32_t sh) {
  return hadd2(hmul2(ln_norm(x, mean2, ih, il), c1), sh);
}

#define R8(a, i) "+f"(a[i]), "+f"(a[i + 1]), "+f"(a[i + 2]), "+f"(a[i + 3]), "+f"(a[i + 4]), "+f"(a[i + 5]), "+f"(a[i + 6]), "+f"(a[i + 7])
#define D64 "{%0,%1,%2,%3,%4,%5,%6,%7,%8,%9,%10,%11,%12,%13,%14,%15,%16,%17,%18,%19,%20,%21,%22,%23,%24,%25,%26,%27,%28,%29,%30,%31," \
            "%32,%33,%34,%35,%36,%37,%38,%39,%40,%41,%42,%43,%44,%45,%46,%47,%48,%49,%50,%51,%52,%53,%54,%55,%56,%57,%58,%59,%60,%61,%62,%63}"
template <int TB>
__device__ __forceinline__ void mma_ss(float (&d)[64], uint64_t da, uint64_t db, int sc) {
  asm volatile("{\n.reg .pred p;\nsetp.ne.b32 p, %66, 0;\n"
               "wgmma.mma_async.sync.aligned.m64n128k16.f32.bf16.bf16 " D64 ", %64, %65, p, 1, 1, 0, %67;\n}"
               : R8(d, 0), R8(d, 8), R8(d, 16), R8(d, 24), R8(d, 32), R8(d, 40), R8(d, 48), R8(d, 56)
               : "l"(da), "l"(db), "r"(sc), "n"(TB));
}
template <int TB>
__device__ __forceinline__ void mma_rs(float (&d)[64], uint32_t a0, uint32_t a1, uint32_t a2, uint32_t a3, uint64_t db, int sc) {
  asm volatile("{\n.reg .pred p;\nsetp.ne.b32 p, %69, 0;\n"
               "wgmma.mma_async.sync.aligned.m64n128k16.f32.bf16.bf16 " D64 ", {%64,%65,%66,%67}, %68, p, 1, 1, %70;\n}"
               : R8(d, 0), R8(d, 8), R8(d, 16), R8(d, 24), R8(d, 32), R8(d, 40), R8(d, 48), R8(d, 56)
               : "r"(a0), "r"(a1), "r"(a2), "r"(a3), "l"(db), "r"(sc), "n"(TB));
}
#define D128 "{%0,%1,%2,%3,%4,%5,%6,%7,%8,%9,%10,%11,%12,%13,%14,%15,%16,%17,%18,%19,%20,%21,%22,%23,%24,%25,%26,%27,%28,%29,%30,%31," \
             "%32,%33,%34,%35,%36,%37,%38,%39,%40,%41,%42,%43,%44,%45,%46,%47,%48,%49,%50,%51,%52,%53,%54,%55,%56,%57,%58,%59,%60,%61,%62,%63," \
             "%64,%65,%66,%67,%68,%69,%70,%71,%72,%73,%74,%75,%76,%77,%78,%79,%80,%81,%82,%83,%84,%85,%86,%87,%88,%89,%90,%91,%92,%93,%94,%95," \
             "%96,%97,%98,%99,%100,%101,%102,%103,%104,%105,%106,%107,%108,%109,%110,%111,%112,%113,%114,%115,%116,%117,%118,%119,%120,%121,%122,%123,%124,%125,%126,%127}"
#define R128(d, e) R8(d, 0), R8(d, 8), R8(d, 16), R8(d, 24), R8(d, 32), R8(d, 40), R8(d, 48), R8(d, 56), \
                   R8(e, 0), R8(e, 8), R8(e, 16), R8(e, 24), R8(e, 32), R8(e, 40), R8(e, 48), R8(e, 56)
__device__ __forceinline__ void mma256_ss(float (&d)[64], float (&e)[64], uint64_t da, uint64_t db, int sc) {
  asm volatile("{\n.reg .pred p;\nsetp.ne.b32 p, %130, 0;\n"
               "wgmma.mma_async.sync.aligned.m64n256k16.f32.bf16.bf16 " D128 ", %128, %129, p, 1, 1, 0, 1;\n}"
               : R128(d, e) : "l"(da), "l"(db), "r"(sc));
}
__device__ __forceinline__ void mma256_rs(float (&d)[64], float (&e)[64], uint32_t a0, uint32_t a1, uint32_t a2, uint32_t a3, uint64_t db) {
  asm volatile("{\n.reg .pred p;\nsetp.ne.b32 p, 1, 0;\n"
               "wgmma.mma_async.sync.aligned.m64n256k16.f32.bf16.bf16 " D128 ", {%128,%129,%130,%131}, %132, p, 1, 1, 1;\n}"
               : R128(d, e) : "r"(a0), "r"(a1), "r"(a2), "r"(a3), "l"(db));
}
template <int N> __device__ __forceinline__ void keep(float (&a)[N]) {
#pragma unroll
  for (int i = 0; i < N; i++) asm volatile("" : "+f"(a[i])::"memory");
}
template <int N> __device__ __forceinline__ void keep(uint32_t (&a)[N]) {
#pragma unroll
  for (int i = 0; i < N; i++) asm volatile("" : "+r"(a[i])::"memory");
}

#define STAMP(idx) do {} while (0)
#define PROF(grp, cond, idx) do {} while (0)

constexpr float SCL2 = 1.4426950408889634f * 0.08838834764831845f;

__device__ __forceinline__ void pack_p(const float (&s)[64], uint32_t (&p)[32]) {
#pragma unroll
  for (int i = 0; i < 32; i++) p[i] = pack_bf(s[2 * i], s[2 * i + 1]);
}

__device__ __forceinline__ void issue_qk(float (&s)[64], uint32_t q0, uint32_t q1, uint32_t kslot) {
  const uint64_t db = make_desc(kslot, 16, 1024), da0 = make_desc(q0, 16, 1024), da1 = make_desc(q1, 16, 1024);
#pragma unroll
  for (int kk = 0; kk < 8; kk++) mma_ss<0>(s, (kk < 4 ? da0 : da1) + (kk & 3) * 2, db + (kk >> 2) * 1024 + (kk & 3) * 2, kk != 0);
}
__device__ __forceinline__ void issue_pv(float (&o)[64], uint32_t (&p)[32], uint32_t vslot, int acc) {
  uint64_t db = make_desc(vslot, 16384, 1024);
#pragma unroll
  for (int kk = 0; kk < 8; kk++)
    mma_rs<1>(o, p[4 * kk], p[4 * kk + 1], p[4 * kk + 2], p[4 * kk + 3], db + kk * 128, kk == 0 ? acc : 1);
}

template <int H>
__device__ __forceinline__ void store_chunk(const float (&a)[64], uint32_t addr) {
#pragma unroll
  for (int i = 8 * H; i < 8 * H + 8; i += 2)
    stmatrix4(addr ^ ((i & 7) << 4), pack_bf(a[4 * i], a[4 * i + 1]), pack_bf(a[4 * i + 2], a[4 * i + 3]),
              pack_bf(a[4 * i + 4], a[4 * i + 5]), pack_bf(a[4 * i + 6], a[4 * i + 7]));
}
template <int H>
__device__ __forceinline__ void store_chunk(const float (&a)[64], float i0, float i1, uint32_t addr) {
#pragma unroll
  for (int i = 8 * H; i < 8 * H + 8; i += 2)
    stmatrix4(addr ^ ((i & 7) << 4), pack_bf(a[4 * i] * i0, a[4 * i + 1] * i0), pack_bf(a[4 * i + 2] * i1, a[4 * i + 3] * i1),
              pack_bf(a[4 * i + 4] * i0, a[4 * i + 5] * i0), pack_bf(a[4 * i + 6] * i1, a[4 * i + 7] * i1));
}
__device__ __forceinline__ float inv_quad_sum(float l) {
  l += __shfl_xor_sync(0xffffffffu, l, 1);
  l += __shfl_xor_sync(0xffffffffu, l, 2);
  return rcp(l);
}

__device__ __forceinline__ void write_table(uint32_t table, bool ca, uint32_t t, const uint4& m0, const uint4& m1) {
  float c0 = untag_sum(m0.x, m1.x), c1 = untag_sum(m0.y, m1.y), c2 = untag_sum(m0.z, m1.z), c3 = untag_sum(m0.w, m1.w);
  if (ca) { c0 = 1.f + rbf(c0); c1 = 1.f + rbf(c1); c2 = 1.f + rbf(c2); c3 = 1.f + rbf(c3); }
  const uint32_t d = table + (t >> 2) * 64 + (t & 1) * 32 + (t & 2) * 2 + (ca ? 0 : 8);
  sts1(d, pack_bf(c0, c1));
  sts1(d + 16, pack_bf(c2, c3));
}

__device__ __forceinline__ void ln_scalars(float mean, float var, float& mb, float& sd) {
  mb = rbf(mean);
  float r; asm("sqrt.approx.ftz.f32 %0, %1;" : "=f"(r) : "f"(rbf(rbf(var) + 1e-5f)));
  sd = rbf(r);
}

__global__ void __cluster_dims__(2, 1, 1) __launch_bounds__(384, 1) fused_kernel(const __grid_constant__ Maps maps, const Ptrs P) {
  extern __shared__ __align__(1024) uint8_t smem_raw[];
  const uint32_t base = smem_u32(smem_raw);
  const int tid = threadIdx.x, lane = tid & 31;
  const int warp = __shfl_sync(0xffffffffu, tid >> 5, 0);
  const int b = blockIdx.x;
  PROF(31, tid == 0, 0);

  if (b >= NMAIN) {
    float* sc = reinterpret_cast<float*>(smem_raw);
    float* red = sc + DM;
    for (int k = tid; k < DM; k += 384) sc[k] = rbf(silu_f(__bfloat162float(P.c[k])));
    __syncthreads();
    if (tid < 256) {
      const int col = 2048 + (b - NMAIN) * 1024 + (tid & 127) * 8, r0 = (tid >> 7) * 512;
      float acc[8];
#pragma unroll
      for (int e = 0; e < 8; e++) acc[e] = 0.f;
#pragma unroll 1
      for (int r = r0; r < r0 + 512; r += HU) {
        uint4 w[HU];
#pragma unroll
        for (int u = 0; u < HU; u++) w[u] = ldg_stream4(P.w_mod + (size_t)(r + u) * NMOD + col);
#pragma unroll
        for (int u = 0; u < HU; u++) {
          float s = sc[r + u];
          acc[0] += s * bf_lo(w[u].x); acc[1] += s * bf_hi(w[u].x); acc[2] += s * bf_lo(w[u].y); acc[3] += s * bf_hi(w[u].y);
          acc[4] += s * bf_lo(w[u].z); acc[5] += s * bf_hi(w[u].z); acc[6] += s * bf_lo(w[u].w); acc[7] += s * bf_hi(w[u].w);
        }
      }
      if (tid >= 128) {
#pragma unroll
        for (int e = 0; e < 8; e++) red[(tid & 127) * 8 + e] = acc[e];
      }
      const uint32_t tag = ld_relaxed(&g_epoch) % 3 + 1;
      bar_sync(1, 256);
      if (tid < 128) {
        uint32_t o[8];
#pragma unroll
        for (int e = 0; e < 8; e++) o[e] = __float_as_uint(rbf(acc[e] + red[tid * 8 + e])) | tag;
        st_relaxed4(g_mod + col, o[0], o[1], o[2], o[3]);
        st_relaxed4(g_mod + col + 4, o[4], o[5], o[6], o[7]);
        const uint4 wr = ldg_nc4(P.w_r + tid * 8);
        const uint32_t wv[4] = {wr.x, wr.y, wr.z, wr.w};
        float dsum = 0.f;
#pragma unroll
        for (int e = 0; e < 8; e++) {
          const float m = bf_hi(o[e]);
          dsum += (b == NMAIN + 2 ? rbf(1.f + m) : m) * ((e & 1) ? bf_hi(wv[e >> 1]) : bf_lo(wv[e >> 1]));
        }
#pragma unroll
        for (int k = 16; k > 0; k >>= 1) dsum += __shfl_xor_sync(0xffffffffu, dsum, k);
        if (lane == 0) st_relaxed(g_mod + (b - NMAIN) * 4 + warp, tagf(dsum, tag));
      }
    }
    PROF(2, tid == 0, 1);
    return;
  }

  const int rank = b & 1;
  const int rb = ((b >> 4) << 1) | rank, cj = (b >> 1) & 7;
  const bool late = b & 4;
  const uint32_t bfull = base + OFF_BAR, bempty = bfull + NSLOT * 8;
  const uint32_t gfull = bempty + NSLOT * 8, gempty = gfull + 32;
  const uint32_t bar_ofull = gempty + 32;
  const uint32_t bar_ofree = bar_ofull + 32;
  const uint32_t bar_par = bar_ofree + 32;
  const uint32_t bar_mod = bar_par + 8;
  const uint32_t bar_pread = bar_mod + 8;
  const uint32_t bar_xres = bar_pread + 8;
  const uint32_t bar_ring = bar_xres + 8;
  const uint32_t bar_box = bar_ring + 24;
  const uint32_t bar_go = bar_box + 96;
  const uint32_t bar_go2 = bar_go + 16;
  const uint32_t bar_cnt = bar_go + 24;
  const uint32_t xfull = bar_go + 40, xempty = xfull + 32;
  const uint32_t bar_hw = xempty + 32, bar_hx = bar_hw + 8;
  const uint32_t bar_hpub = bar_hx + 16;
  const uint32_t bar_win = bar_hpub + 16;
  const uint32_t bar_rx = bar_win + 8;
  const uint32_t bar_sel = bar_rx + 8;
  const uint32_t bar_gate = bar_sel + 8;
  const uint32_t bar_rel = bar_gate + 8;
  const uint32_t bar_od = bar_rel + 8;
  const uint32_t bar_mod2 = bar_od + 8;
  const uint32_t bar_res = bar_go + 8;
  const uint32_t stage = base + OFF_STAGE, par = base + OFF_PAR;

  if (warp == 10 && elect_one()) prefetch_map(&maps.wm);
  if (warp == 8 && elect_one()) {
    for (int s = 0; s < NSLOT; s++) { mbar_init(bfull + s * 8, 1); mbar_init(bempty + s * 8, 16); }
    for (int s = 0; s < 4; s++) { mbar_init(gfull + s * 8, 1); mbar_init(gempty + s * 8, 16); mbar_init(xfull + s * 8, 1); mbar_init(xempty + s * 8, 8); mbar_init(bar_ofree + s * 8, 1); mbar_init(bar_ofull + s * 8, 128); }
    mbar_init(bar_par, 64); mbar_init(bar_mod, 256); mbar_init(bar_pread, 2); mbar_init(bar_xres, 1);
    mbar_init(bar_ring, 8); mbar_init(bar_ring + 8, 8); mbar_init(bar_ring + 16, 8);
    mbar_init(bar_go, 1); mbar_init(bar_go2, 1); mbar_init(bar_cnt, 1); mbar_init(bar_cnt + 8, 1); mbar_init(bar_hpub, 8); mbar_init(bar_hpub + 8, 8); mbar_init(bar_res, 1); mbar_init(bar_win, 1); mbar_init(bar_rx, 1); mbar_init(bar_sel, 64); mbar_init(bar_gate, 8); mbar_init(bar_rel, 8); mbar_init(bar_od, 1); mbar_init(bar_mod2, 64);
    for (int s = 0; s < 12; s++) mbar_init(bar_box + s * 8, 1);
    asm volatile("fence.mbarrier_init.release.cluster;" ::: "memory");
    prefetch_map(&maps.x); prefetch_map(&maps.wq); prefetch_map(&maps.k); prefetch_map(&maps.v);
  }
  if (warp == 9 && elect_one()) {
    mbar_init(bar_hw, 1); mbar_init(bar_hx, 1); mbar_init(bar_hx + 8, 1);
    asm volatile("fence.mbarrier_init.release.cluster;" ::: "memory");
    mbar_expect_tx(bar_hw, 32768);
    mbar_expect_tx(bar_hx, 16384);
    mbar_expect_tx(bar_hx + 8, 16384);
    const __nv_bfloat16* xs = P.x + (size_t)(rb * 128 + cj * 16) * DM;
    bulk_load(base + 2 * GST_BYTES, xs, 16384, bar_hx);
    if (!late) {
      tma2d(stage, &maps.wm, (b >> 1) * 32, rank * 512, bar_hw);
      tma2d(stage + 16384, &maps.wm, (b >> 1) * 32, rank * 512 + 256, bar_hw);
    }
    bulk_load(base + 3 * GST_BYTES, xs + 8 * DM, 16384, bar_hx + 8);
  }
  cluster_arrive();

  if (warp >= 8) {
    asm volatile("setmaxnreg.dec.sync.aligned.u32 40;");
    if (warp < 10) bar_arrive(1, 320);
    const uint32_t epoch = ld_relaxed(&g_epoch);
    cluster_wait();
    if (warp == 8) {
      const int kvrow = (cj >> 1) * SK + (SK - WIN);
      int wch = cj * 8 + rank * 2;
#pragma unroll 1
      for (int ps = 0; ps < 3; ps++) {
        const CUtensorMap* mw = ps == 2 ? &maps.wo : &maps.wq;
        const uint32_t xt = ps == 1 ? XT1 : XT2, wt = ps == 0 ? WT0 : (ps == 1 ? WT1 : WT2);
        const int nst = ps == 2 ? 32 : 16;
#pragma unroll 1
        for (int i = 0; i < nst; i++) {
          const uint32_t bf = gfull + (i & 3) * 8;
          const int kt = ps == 2 ? (((cj & 1) * 4 + ((i >> 1) & 3)) * 4 + (i >> 3)) * 2 + (i & 1) : (ps ? i : slice_of(i) + (b & 14)) & 15;
          const uint32_t wd = base + unit_of(wt, i & 3) + rank * UNIT, xd = base + unit_of(xt, i & 3);
          const uint8_t* xs = g_act + (uint32_t)(rb * 80 + (ps - 1) * 16 + kt) * UNIT;
          if (ps == 0 && i == HD) mbar_wait(bar_mod, 0);
          if (ps == 2 && (i & 7) == 0 && i != 8) mbar_wait(i ? bar_cnt + i - 16 : bar_ofree + 24, 0);
          if ((i & 7) == 0) fence_async();
          if (i == RES0) mbar_wait(bar_res, 0);
          mbar_wait(bf, ((i >> 2) & 1) ^ 1);
          if (elect_one()) {
            mbar_expect_tx(bf, ps ? GST_BYTES : 2 * UNIT);
            if (ps && i < 2) bulk_load_stream(xd, xs, UNIT, bf);
            mbar_arrive_pred(bar_go, i == GOST);
            mbar_arrive_pred(bar_go2, ps == 1 && i == PG0);
            mbar_arrive_pred(bar_od, ps && i == (ps == 1 ? ODS1 : ODS) + 1);
            if (i == RES0) mbar_expect_tx(bar_xres, 32768);
          }
          const int wk = (i == 31 ? kt ^ (rank * 32) : kt) * 64, wc = i == 31 ? cj * 2 : wch;
          const uint64_t xp = i == 31 ? l2_normal() : l2_stream();
          mbar_wait(ps && i < 4 ? bempty + i * 8 : gempty + (i & 3) * 8, ((i >> 2) & 1) ^ 1);
          if (elect_one()) {
            tma3d_mc<true>(wd, mw, 0, wk, wc, bf);
            if (ps && i > 2) bulk_load_stream(xd, xs, UNIT, bf, xp);
            if (i == RES0 || i == RES1) tma2d(base + OFF_RES + (i == RES1) * UNIT, &maps.x, cj * 128 + (i == RES1) * 64, rb * 128, bar_xres);
          }
          if (ps && i == 2) {
            mbar_wait(bar_ofree + (ps - 1) * 16, 0);
            if (elect_one()) bulk_load_stream(xd, xs, UNIT, bf);
          }
        }
        if (ps == 2) break;
        wch = ps ? ((wch >> 3) ^ rank) * 2 : wch + 4;
#pragma unroll 1
        for (int u = 0; u < 16; u++) {
          const bool isk = (u == 0) || ((u & 1) && u < 15);
          const int blk = (isk ? (u + 1) >> 1 : (u == 15 ? 7 : (u >> 1) - 1)) & 3;
          const uint32_t sl = base + unit_of(ps ? AT1 : AT0, u & 3) + rank * UNIT, bf = bfull + (u & 3) * 8;
          mbar_wait(bf, ((u >> 2) & 1) ^ 1);
          if (elect_one()) mbar_expect_tx(bf, SLOT_BYTES);
          mbar_wait(u < 4 ? gempty + ((u + 1) >> 1) * 8 : bempty + (u & 3) * 8, ((u >> 2) & 1) ^ 1);
          if (elect_one()) {
            if (ps && u >= 7 && u != 8) tma3d_mc<true>(sl, isk ? &maps.k : &maps.v, 0, kvrow + blk * 128, rank, bf);
            else tma3d_mc<false>(sl, isk ? &maps.k : &maps.v, 0, kvrow + blk * 128, rank, bf);
          }
        }
      }
      if (elect_one()) mbar_expect_tx(bar_rx, UNIT);
      mbar_wait(bar_rel, 0);
      if (elect_one()) {
        bulk_load_stream(base + UNIT, g_act + (uint32_t)(rb * 80 + 16 + 63 - (cj & 1) * 32) * UNIT, UNIT, bar_rx);
      }
      if (b < NFFN) {
#pragma unroll 1
        for (int u = 0; u < 12; u++) {
          const uint32_t dst = base + unit_of(u < 4 ? FT_G : (u < 8 ? FT_U : FT_D), u & 3);
          if (elect_one()) mbar_expect_tx(bar_box + u * 8, UNIT);
          if (u == 0 || u == 2 || u == 8) mbar_wait(bar_ring + (u == 8 ? 16 : u * 4), 0);
          const int fp = u < 8 ? FPACE0 : FPACE;
          if (u >= fp) mbar_wait(bar_box + (u - fp) * 8, 0);
          if (elect_one()) {
            if (u < 8) tma2d(dst, u < 4 ? &maps.wg : &maps.wu, b * 32, (u & 3) * 256, bar_box + u * 8);
            else tma3d(dst, &maps.wd, 0, b * 32, (u - 8) * 4, bar_box + u * 8);
          }
        }
      }
    } else if (warp == 9) {
      const uint32_t target = 8 * (epoch + 1);
      uint32_t hmask = 0;
#pragma unroll 1
      for (int i = 0; i < 16; i++) {
        if (i == HDX) mbar_wait(bar_mod, 0);
        const int kt = (2 * cj + slice_of(i)) & 15;
        const uint32_t need = i == 15 ? 0xffffu : 1u << kt;
        if (i >= NRS && (hmask & need) != need) {
          uint32_t n = 0;
          do { hmask = __ballot_sync(0xffffffffu, ld_acquire(&g_cnt_h[rb * 32 + (lane & 15)]) == epoch + 1); watchdog(n); } while ((hmask & need) != need);
          PROF(1, lane == 0 && i == NRS, 26);
          fence_async();
        }
        mbar_wait(xempty + (i & 3) * 8, ((i >> 2) & 1) ^ 1);
        if (elect_one()) {
          mbar_expect_tx(xfull + (i & 3) * 8, UNIT);
          if (i < NRS) tma2d(base + (i & 3) * GST_BYTES, &maps.x, kt * 64, rb * 128, xfull + (i & 3) * 8);
          else bulk_load_stream(base + (i & 3) * GST_BYTES, g_act + (uint32_t)(rb * 80 + kt) * UNIT, UNIT, xfull + (i & 3) * 8);
        }
      }
      prefetch_map(&maps.wo);
#pragma unroll 1
      for (int t = 0; t < 4; t++) {
        if (t & 1) mbar_wait(bar_od, t >> 1);
        const int ops = OPS >> (t & 1);
#pragma unroll 1
        for (int p = 0; p < 32768; p += ops) {
          const uint32_t w = p >> 14, c = (p >> 13) & 1, off = w * 8192 + (p & 8191);
          mbar_wait(bar_ofull + (t & 1) * 16 + w * 8, t >> 1);
          if (elect_one()) {
            bulk_store(g_act + (uint32_t)(rb * 80 + 16 + (cj * 4 + t) * 2 + c) * UNIT + off, base + unit_of(QT, 2 * t + c) + off, ops);
            asm volatile("cp.async.bulk.commit_group;" ::: "memory");
            asm volatile("cp.async.bulk.wait_group.read 0;" ::: "memory");
          }
        }
        if (elect_one()) {
          mbar_arrive(t < 3 ? bar_ofree + t * 8 : bar_res);
          asm volatile("cp.async.bulk.wait_group 0;" ::: "memory");
          fence_async();
          red_release(&g_cnt_o[((rb * 4 + t) * 2 + (cj >> 2)) * 32], 2);
        }
        if (t) {
          wait_counter(&g_cnt_o[(rb * 8 + 2 * t + (cj & 1)) * 32], target);
          if (t & 1) wait_counter(&g_cnt_o[(rb * 8 + (t == 1 ? cj & 1 : 7 - (cj & 1))) * 32], target);
          if (elect_one()) mbar_arrive(t == 1 ? bar_ofree + 24 : bar_cnt + t * 8 - 16);
        }
      }
      PROF(2, lane == 0, 27);
      const uint32_t tag = epoch % 3 + 1;
      const uint32_t* inbox = g_cand + (b >> 1) % CR * 512 + (lane & 15) * CS;
      mbar_wait(bar_ring + 16, 0);
      uint32_t c0 = ld_relaxed(inbox), n = 0;
#define CAND_STEP(cv)                                                                                        \
      {                                                                                                      \
        const bool valid = (cv & 3u) == tag, all = __all_sync(0xffffffffu, valid);                           \
        const uint32_t best = __reduce_max_sync(0xffffffffu, valid ? cv : 0u);                               \
        const uint32_t blk = __ffs(__ballot_sync(0xffffffffu, cv == best)) - 1;                              \
        if (best) sts2(par + PAR_CONST + 56, best, (blk << 7 | (~best >> 2 & 127)) | (all ? 0x1800 : 0x800)); \
        if (all) break;                                                                                      \
        cv = ld_relaxed(inbox);                                                                              \
      }
      while (true) { CAND_STEP(c0) watchdog(n); }
    } else {
      const int t2 = tid - 320;
      if (late && warp == 10) {
        mbar_wait(bar_hx, 0);
        if (elect_one()) {
          tma2d(stage, &maps.wm, (b >> 1) * 32, rank * 512, bar_hw);
          tma2d(stage + 16384, &maps.wm, (b >> 1) * 32, rank * 512 + 256, bar_hw);
        }
      }
      {
        const uint32_t tag = epoch % 3 + 1;
        mbar_wait(bar_hx + 8, 0);
        mbar_wait(bar_hw, 0);
        __nanosleep(late ? OSL2 : OSL);
        {
          const uint32_t t7 = (warp & 1) * 64 + (lane >> 4) * 32 + 16 + (lane & 15);
          const uint32_t* pm = g_modp + ((cj * 128 + t7 * 4) & (DM - 1));
          uint4 m0, m1, m2, m3;
          uint32_t n = 0;
          do {
            m0 = ld_relaxed4(pm); m1 = ld_relaxed4(pm + 2 * DM); m2 = ld_relaxed4(pm + DM); m3 = ld_relaxed4(pm + 3 * DM);
            watchdog(n);
          } while (!__all_sync(0xffffffffu, tag_ok(m0, tag) && tag_ok(m1, tag) && tag_ok(m2, tag) && tag_ok(m3, tag)));
          write_table(par, false, t7, m0, m1);
          write_table(par, true, t7, m2, m3);
          mbar_arrive(bar_mod2);
        }
      }
      mbar_wait(bar_hpub + (warp & 1) * 8, 0);
      PROF(1, t2 == 0, 24);
#pragma unroll 1
      for (int c = 0; c < 8; c++) {
        const uint32_t off = (warp & 1) * UNIT + c * 2048 + lane * 16;
        uint8_t* dst = g_act + (uint32_t)(rb * 80 + cj * 2) * UNIT + off;
        const uint4 v0 = lds4(stage + off), v1 = lds4(stage + off + 512), v2 = lds4(stage + off + 1024), v3 = lds4(stage + off + 1536);
        stg4(dst, v0); stg4(dst + 512, v1); stg4(dst + 1024, v2); stg4(dst + 1536, v3);
      }
      __syncwarp();
      PROF(1, t2 == 0, 15);
      if (lane == 0) {
        mbar_arrive(bar_pread);
        red_release(&g_cnt_h[rb * 32 + cj * 2 + (warp & 1)], 1);
        PROF(1, t2 == 0, 25);
        prefetch_map(&maps.wg); prefetch_map(&maps.wu); prefetch_map(&maps.wd); prefetch_map(&maps.out);
      }
      __syncwarp();
      if (b < NFFN) {
        mbar_wait(bar_go2, 0);
        const __nv_bfloat16* pg = ((b & 1) ? P.w_up : P.w_gate) + (b >> 1) * 64 + (size_t)t2 * FF;
        const __nv_bfloat16* pd = P.w_down + (size_t)b * 32768 + t2 * 64;
        PROF(2, t2 == 0, 13);
#pragma unroll 1
        for (int i = 0; i < WN; i += WB) {
          uint32_t v[WB];
#pragma unroll
          for (int u = 0; u < WB; u++) {
            const int k = i + u;
            asm volatile("ld.global.cg.L2::128B.u32 %0, [%1];" : "=r"(v[u]) : "l"(k < 16 ? pg + (size_t)k * 64 * FF : pd + (k - 16) * 4096));
          }
#pragma unroll
          for (int u = 1; u < WB; u++) v[0] ^= v[u];
          sts1(par + PAR_SINK + t2 * 4, v[0]);
        }
        PROF(2, t2 == 0, 14);
      }
      const uint32_t tag = epoch % 3 + 1;
      mbar_wait(bar_go, 0);
      bar_sync(4, 64);
      if (warp == 10) {
        const uint32_t* src = g_mod + 2 * DM + cj * 128 + lane * 4;
        const uint2 wr = *reinterpret_cast<const uint2*>(P.w_r + cj * 128 + lane * 4);
        uint4 vga, vsb, vcb, vgb;
        uint32_t n = 0;
        do {
          vga = ld_relaxed4(src); vsb = ld_relaxed4(src + DM); vcb = ld_relaxed4(src + 2 * DM); vgb = ld_relaxed4(src + 3 * DM);
          watchdog(n);
        } while (!__all_sync(0xffffffffu, tag_ok(vga, tag) && tag_ok(vsb, tag) && tag_ok(vcb, tag) && tag_ok(vgb, tag)));
        const float c0 = rbf(1.f + bf_hi(vcb.x)), c1 = rbf(1.f + bf_hi(vcb.y)), c2 = rbf(1.f + bf_hi(vcb.z)), c3 = rbf(1.f + bf_hi(vcb.w));
        const float a0 = c0 * bf_lo(wr.x), a1 = c1 * bf_hi(wr.x), a2 = c2 * bf_lo(wr.y), a3 = c3 * bf_hi(wr.y);
        const uint32_t h0 = pack_bf(a0, a1), h1 = pack_bf(a2, a3);
        const uint32_t t1 = par + PAR_T1 + (lane >> 2) * 64 + (lane & 1) * 32 + (lane & 2) * 2;
        sts1(t1, h0); sts1(t1 + 8, pack_bf(a0 - bf_lo(h0), a1 - bf_hi(h0)));
        sts1(t1 + 16, h1); sts1(t1 + 24, pack_bf(a2 - bf_lo(h1), a3 - bf_hi(h1)));
        const uint32_t tg = par + PAR_SINK + (lane >> 3) * 64 + (lane & 1) * 32 + (lane & 6) * 2;
        sts1(tg, __byte_perm(vga.x, vga.y, 0x7632)); sts1(tg + 16, __byte_perm(vga.z, vga.w, 0x7632));
        sts4(par + PAR_T2 + lane * 32, make_uint4(pack_bf(c0, c1), __byte_perm(vsb.x, vsb.y, 0x7632), __byte_perm(vgb.x, vgb.y, 0x7632), __byte_perm(vga.x, vga.y, 0x7632)));
        sts4(par + PAR_T2 + lane * 32 + 16, make_uint4(pack_bf(c2, c3), __byte_perm(vsb.z, vsb.w, 0x7632), __byte_perm(vgb.z, vgb.w, 0x7632), __byte_perm(vga.z, vga.w, 0x7632)));
      } else {
        const uint4 g = poll4((lane & 8) ? g_mod + 8 - (lane & 1) * 4 : g_mod + 5 * DM + (b >> 4) * 128 + (lane & 7) * 16 + (b & 12), tag);
        sts1(par + PAR_CONST + 60, 0);
        if (lane < 8) sts1(par + PAR_CONST + 16 + lane * 4, (b & 2) ? ((b & 1) ? g.w : g.z) : ((b & 1) ? g.y : g.x));
        else if (lane < 10) sts2(par + PAR_CONST + (lane - 8) * 8, __float_as_uint(untag_sum(g.x, g.y) + untag_sum(g.z, g.w)), epoch);
      }
      __syncwarp();
#pragma unroll 1
      for (int q = 0; q < 32; q++) {
        st_b128(g_xch + ((size_t)b * 8 * 256 + q * 64 + t2) * 4, (epoch & 1) << 16, 0, 0, 0);
        __nanosleep(RSL);
      }
      for (int q = 0; q < 2; q++) st_relaxed4(g_stats + (((rb * 8 + q * 4 + (t2 >> 4)) * 8 + cj) * 16 + (t2 & 15)) * 4, 0, 0, 0, 0);
      if (b < NFFN)
        for (int q = 0; q < 2; q++) st_relaxed4(ypart_slot(b, q * 64 + t2), 0, 0, 0, 0);
      st_relaxed4(g_row + rb * 2 * DM + (t2 >> 5) * DM + cj * 128 + (t2 & 31) * 4, 0, 0, 0, 0);
      __threadfence();
      mbar_arrive(bar_par);
      mbar_wait(bar_gate, 0);
      uint32_t have = 0, n = 0;
      while (true) {
        const uint32_t st = lds1(par + PAR_CONST + 60) >> 7;
        if ((st & 31) != have) {
          const uint32_t* hsrc = g_row + (st & 15) * 2 * DM + t2 * 4;
          uint4 hv[4];
          bool ok = true;
#pragma unroll
          for (int i = 0; i < 4; i++) hv[i] = ld_pairs(hsrc + i * 256);
#pragma unroll
          for (int i = 0; i < 4; i++) {
            sts2(base + ((FT_G >> i * 4) & 15) * UNIT + (warp & 1) * 8192 + 256 + lane * 8, hv[i].x, hv[i].z);
            ok = ok && hv[i].y == tag && hv[i].w == tag;
          }
          have = __all_sync(0xffffffffu, ok) ? st & 31 : 0;
        }
        if ((st ^ have) == 32) break;
        watchdog(n);
      }
      mbar_arrive(bar_sel);
    }
    __syncwarp();
    cluster_arrive();
    {
      const uint32_t tag = epoch % 3 + 1, t3 = tid - 256;
      mbar_wait(bar_win, 0);
      uint2 win = lds2(par + PAR_CONST + 56);
      win.y &= 0x7ff;
      const uint32_t* fsrc = g_row + (win.y >> 7) * 2 * DM + (b >> 4) * 128 + (t3 & 7) * 16 + (b & 6) * 2 + ((b >> 2) & 2);
      const uint32_t* ysrc = ypart_slot(min(t3, NFFN - 1), b);
      uint2 fh = ld_pair(fsrc), fx = ld_pair(fsrc + DM);
      uint4 ya = ld_b128(ysrc);
      const float rwin = __uint_as_float(((int)win.x < 0 ? win.x & 0x7fffffffu : ~win.x) & ~0x1ffu);
      const float rs = rbf(rcp(1.f + __expf(-rbf(rwin))));
      uint32_t n = 0;
      while (__any_sync(0xffffffffu, fh.y != tag || fx.y != tag)) { fh = ld_pair(fsrc); fx = ld_pair(fsrc + DM); watchdog(n); }
      while (true) {
        const bool miss = ((ya.x & 1) | (ya.y & 1) << 1) != tag;
        if (!__any_sync(0xffffffffu, miss)) break;
        if (miss) ya = ld_b128(ysrc);
        watchdog(n);
      }
      PROF(8, t3 == 0, 5);
      float y[8] = {bf_lo(ya.x & ~1u), bf_hi(ya.x), bf_lo(ya.y & ~1u), bf_hi(ya.y), bf_lo(ya.z), bf_hi(ya.z), bf_lo(ya.w), bf_hi(ya.w)};
#pragma unroll
      for (int h = 4; h > 0; h >>= 1) {
        const bool up = lane & (h * 2);
#pragma unroll
        for (int e = 0; e < h; e++) y[e] = (up ? y[e + h] : y[e]) + __shfl_xor_sync(0xffffffffu, up ? y[e] : y[e + h], h * 2);
      }
      y[0] += __shfl_xor_sync(0xffffffffu, y[0], 1);
      if (!(lane & 1)) sts1(par + PAR_RED + 64 + t3 * 2, __float_as_uint(y[0]));
      bar_sync(4, 128);
      if (t3 < 8) {
        float y0 = 0.f;
#pragma unroll
        for (int w7 = 0; w7 < 7; w7++) y0 += __uint_as_float(lds1(par + PAR_RED + 64 + w7 * 32 + t3 * 4));
        const uint32_t gv = lds1(par + PAR_CONST + 16 + t3 * 4);
        const uint32_t upd = hmul2(pack_bf(y0, y0), pack_bf(rs, rs));
        const uint32_t r = hadd2(fx.x, hmul2(__byte_perm(gv, gv, 0x3232), hadd2(fh.x, upd)));
        reinterpret_cast<uint16_t*>(P.out)[(size_t)win.y * DM + (b >> 4) * 128 + t3 * 16 + (b & 15)] = (b & 1) ? r >> 16 : r;
        if (b == 0 && t3 == 0) st_relaxed(&g_epoch, epoch + 1);
      }
      PROF(31, t3 == 0, 36);
    }
    cluster_wait();
  } else {
    const int wg = warp >> 2;

    uint32_t tag;
    {
      uint32_t* const pmod = g_modp + rank * 2 * DM + (b >> 1) * 32 + lane;
      uint32_t* const pln = g_ln1 + (rb * 128 + cj * 16 + warp) * 4;
      uint32_t sc[8];
#pragma unroll
      for (int k = 0; k < 8; k++) sc[k] = ldg_nc1(P.c + rank * 512 + warp * 64 + k * 8 + (lane & 3) * 2);
      const uint32_t epoch = ld_relaxed(&g_epoch);
      if (warp == 0) st_relaxed(pmod, 0);
      if (lane == 0) { st_b128(pln, 0, 0, 0, 0); st_b128(pln + 32, 0, 0, 0, 0); }
      asm volatile("setmaxnreg.inc.sync.aligned.u32 232;");
      bar_sync(1, 320);
#pragma unroll
      for (int k = 0; k < 8; k++) sc[k] = pack_bf(silu_f(bf_lo(sc[k])), silu_f(bf_hi(sc[k])));
      keep(sc);
      tag = epoch % 3 + 1;
#pragma unroll
      for (int part = 0; part < 4; part++) {
        if (!(part & 1)) {
          const uint32_t xa = base + (2 + part / 2) * GST_BYTES + warp * 2048 + lane * 16;
          mbar_wait(bar_hx + part * 4, 0);
          float s0 = 0.f, s1 = 0.f, q0 = 0.f, q1 = 0.f;
#pragma unroll
          for (int q = 0; q < 4; q++) {
            const uint4 xv = lds4(xa + q * 512);
            const uint32_t u[4] = {xv.x, xv.y, xv.z, xv.w};
#pragma unroll
            for (int e = 0; e < 4; e++) { const float lo = bf_lo(u[e]), hi = bf_hi(u[e]); s0 += lo; s1 += hi; q0 += lo * lo; q1 += hi * hi; }
          }
          s0 += s1; q0 += q1;
#pragma unroll
          for (int o = 16; o > 0; o >>= 1) { s0 += __shfl_xor_sync(0xffffffffu, s0, o); q0 += __shfl_xor_sync(0xffffffffu, q0, o); }
          const float mean = s0 * (1.f / DM);
          float mb, sd;
          ln_scalars(mean, fmaxf(q0 * (1.f / DM) - mean * mean, 0.f), mb, sd);
          uint32_t ih, il;
          split_inv(sd, ih, il);
          if (lane == 0) st_b128(pln + part * 16, pack_bf(mb, mb), ih, il, tag);
          PROF(1, tid == 0 && part == 2, 4);
        } else if (late == (part == 3)) {
          const uint32_t fr = (lane & 7) + (lane >> 4) * 8, tq = lane & 3;
          const uint32_t wa = stage + warp * 4096 + fr * 64 + ((((lane >> 3) & 1) ^ ((fr >> 1) & 3)) << 4);
          float d0[4] = {0.f, 0.f, 0.f, 0.f}, d1[4] = {0.f, 0.f, 0.f, 0.f};
          mbar_wait(bar_hw, 0);
#pragma unroll
          for (int ks = 0; ks < 4; ks++) {
            uint32_t w[8];
            ldmatrix4t(wa + ks * 1024, w[0], w[1], w[2], w[3]);
            ldmatrix4t((wa ^ 32) + ks * 1024, w[4], w[5], w[6], w[7]);
            mma16816(d0, w[0], w[1], w[2], w[3], sc[2 * ks], sc[2 * ks + 1]);
            mma16816(d1, w[4], w[5], w[6], w[7], sc[2 * ks], sc[2 * ks + 1]);
          }
          sts1(base + 2 * GST_BYTES + warp * 2048 + (tq * 8 + (lane >> 2)) * 4, __float_as_uint((tq & 2) ? ((tq & 1) ? d1[2] : d1[0]) : ((tq & 1) ? d0[2] : d0[0])));
          bar_sync(1, 256);
          if (warp == 0) {
            float s = 0.f;
#pragma unroll
            for (int w8 = 0; w8 < 8; w8++) s += __uint_as_float(lds1(base + 2 * GST_BYTES + w8 * 2048 + lane * 4));
            st_relaxed(pmod, (__float_as_uint(s) & ~3u) | tag);
          }
          PROF(1, tid == 0, 3);
        }
      }
      cluster_wait();
      if (wg == 1) bar_arrive(2, 256);
    }

    float f0 = 0.f, f1 = 0.f;
    const uint32_t rempty = lane < 2 ? mapa(bempty, lane & 1) : 0;
    constexpr uint32_t GE = NSLOT * 8 + 32;
    float o[64], s[64];
#pragma unroll 1
    for (int ps = 0; ps < 3; ps++) {
      {
        const uint32_t xt = ps == 1 ? XT1 : XT2, wt = ps == 1 ? WT1 : WT2;
        const int nst = ps == 2 ? 28 : 14;
        if (ps == 0) {
          float ga[64], gb[64];
#pragma unroll
          for (int i = 0; i < 64; i++) { ga[i] = 0.f; gb[i] = 0.f; }
          uint32_t a[2][16];
          const uint32_t l = fresh_lane();
          uint32_t fa[4];
#pragma unroll
          for (int kk = 0; kk < 4; kk++) fa[kk] = (base + wg * 8192 + frag_offset(warp)) ^ (kk * 32);
          const uint32_t mt = par + (l & 3) * 16;
          auto fetch = [&](int i, uint32_t (&f)[16], uint32_t z) {
            mbar_wait(xfull + (i & 3) * 8, i >> 2);
#pragma unroll
            for (int kk = 0; kk < 4; kk++) ldmatrix4(fa[kk] + (i & 3) * GST_BYTES + z, f[4 * kk], f[4 * kk + 1], f[4 * kk + 2], f[4 * kk + 3]);
          };
          const bool oddw = warp & 2;
          uint4 r0, r1;
          {
            const uint32_t t7 = (warp & 1) * 64 + (l >> 4) * 32 + (l & 15);
            const uint32_t* pm = g_modp + wg * DM + ((cj * 128 + t7 * 4) & (DM - 1));
            const uint32_t* pr = g_ln1 + (rb * 128 + warp * 16 + (l >> 2)) * 4;
            uint4 m0 = make_uint4(tag, tag, tag, tag), m1 = m0;
            if (!oddw) { m0 = ld_relaxed4(pm); m1 = ld_relaxed4(pm + 2 * DM); }
            r0 = ld_b128(pr); r1 = ld_b128(pr + 32);
            fetch(0, a[0], 0); fetch(1, a[1], 0);
            uint32_t n = 0;
            bool written = false;
#pragma unroll 1
            while (true) {
              uint32_t miss;
              asm volatile("{ .reg .pred p0, p1, p2, p3; .reg .b32 t, u;\n"
                           "lop3.b32 t, %1, %2, %19, 0x7e; lop3.b32 u, %3, %4, %19, 0x7e; or.b32 t, t, u; and.b32 t, t, 3; setp.ne.u32 p0, t, 0;\n"
                           "lop3.b32 t, %5, %6, %19, 0x7e; lop3.b32 u, %7, %8, %19, 0x7e; or.b32 t, t, u; and.b32 t, t, 3; setp.ne.u32 p1, t, 0;\n"
                           "setp.ne.u32 p2, %12, %19; setp.ne.u32 p3, %16, %19;\n"
                           "@p0 ld.relaxed.gpu.global.v4.u32 {%1, %2, %3, %4}, [%17];\n"
                           "@p1 ld.relaxed.gpu.global.v4.u32 {%5, %6, %7, %8}, [%17 + 8192];\n"
                           "@p2 ld.relaxed.gpu.global.v4.u32 {%9, %10, %11, %12}, [%18];\n"
                           "@p3 ld.relaxed.gpu.global.v4.u32 {%13, %14, %15, %16}, [%18 + 128];\n"
                           "or.pred p0, p0, p1; or.pred p2, p2, p3; vote.sync.any.pred p0, p0, 0xffffffff; vote.sync.any.pred p2, p2, 0xffffffff;\n"
                           "selp.u32 t, 1, 0, p0; selp.u32 u, 2, 0, p2; or.b32 %0, t, u; }"
                           : "=r"(miss), "+r"(m0.x), "+r"(m0.y), "+r"(m0.z), "+r"(m0.w), "+r"(m1.x), "+r"(m1.y), "+r"(m1.z), "+r"(m1.w),
                             "+r"(r0.x), "+r"(r0.y), "+r"(r0.z), "+r"(r0.w), "+r"(r1.x), "+r"(r1.y), "+r"(r1.z), "+r"(r1.w)
                           : "l"(pm), "l"(pr), "r"(tag) : "memory");
              if (!(miss & 1) && !written) {
                written = true;
                if (!oddw) write_table(par, wg, t7, m0, m1);
                mbar_arrive(bar_mod);
              }
              if (!miss) break;
              watchdog(n);
            }
          }
          const uint32_t zero = r0.w ^ tag;
          auto normalize = [&](uint32_t (&f)[16]) {
#pragma unroll
            for (int k = 0; k < 16; k += 2) { f[k] = ln_norm(f[k], r0.x, r0.y, r0.z); f[k + 1] = ln_norm(f[k + 1], r1.x, r1.y, r1.z); }
          };
          auto modulate = [&](int i, uint32_t (&f)[16]) {
#pragma unroll
            for (int kk = 0; kk < 4; kk++) {
              const uint4 m = lds4(mt + slice_of(i) * 256 + kk * 64);
              f[4 * kk] = hfma2(f[4 * kk], m.x, m.z); f[4 * kk + 1] = hfma2(f[4 * kk + 1], m.x, m.z);
              f[4 * kk + 2] = hfma2(f[4 * kk + 2], m.y, m.w); f[4 * kk + 3] = hfma2(f[4 * kk + 3], m.y, m.w);
            }
            keep(f);
            mbar_arrive_pred(xempty + (i & 3) * 8, l == 0);
          };
          auto publish = [&](int u, uint32_t (&f)[16]) {
#pragma unroll
            for (int kk = 0; kk < 4; kk++) stmatrix4(fa[kk] + OFF_STAGE + u * UNIT, f[4 * kk], f[4 * kk + 1], f[4 * kk + 2], f[4 * kk + 3]);
            __syncwarp();
            mbar_arrive_pred(bar_hpub + u * 8, l == 0);
          };
          auto multiply = [&](int i, uint32_t (&f)[16]) {
            mbar_wait(gfull + (i & 3) * 8, i >> 2);
            const uint64_t db = make_desc(base + (i & 3) * GST_BYTES + UNIT, 8192, 1024);
            wg_fence();
#pragma unroll
            for (int kk = 0; kk < 4; kk++) mma256_rs(ga, gb, f[4 * kk], f[4 * kk + 1], f[4 * kk + 2], f[4 * kk + 3], db + kk * 128);
            wg_commit();
          };
          auto next = [&](int i, uint32_t (&f)[16]) {
            wg_wait<1>();
            mbar_arrive_cl(rempty, GE + ((i + 2) & 3) * 8);
            uint32_t z = zero;
#pragma unroll
            for (int k = 0; k < 16; k += 2) asm volatile("lop3.b32 %0, %1, %2, %0, 0xA8;" : "+r"(z) : "r"(f[k]), "r"(f[k + 1]));
            fetch(i, f, z);
            normalize(f);
            if (i == 2) { keep(f); mbar_wait(bar_mod2, 0); }
            modulate(i, f); multiply(i, f);
          };
          normalize(a[0]); normalize(a[1]);
          keep(a[0]); keep(a[1]);
          mbar_wait(bar_mod, 0);
          PROF(1, tid == 0, 2);
          modulate(0, a[0]); multiply(0, a[0]); publish(0, a[0]);
          modulate(1, a[1]); multiply(1, a[1]);
#pragma unroll 1
          for (int i = 2; i < NRS; i += 2) {
            next(i, a[0]);
            if (i == 2) publish(1, a[0]);
            next(i + 1, a[1]);
          }
          wg_wait<1>();
          mbar_arrive_cl(rempty, GE + ((NRS + 2) & 3) * 8);
#pragma unroll 1
          for (int i = NRS; i < 14; i++) {
            mbar_wait(xfull + (i & 3) * 8, (i >> 2) & 1);
            mbar_wait(gfull + (i & 3) * 8, (i >> 2) & 1);
            const uint32_t xa = base + (i & 3) * GST_BYTES;
            const uint64_t da = make_desc(xa + wg * 8192, 16, 1024), db = make_desc(xa + UNIT, 8192, 1024);
            if (i == 13) bar_sync(2 + wg, 256);
            wg_fence();
#pragma unroll
            for (int kk = 0; kk < 4; kk++) mma256_ss(ga, gb, da + kk * 2, db + kk * 128, 1);
            wg_commit();
            if (i == 13) bar_arrive(3 - wg, 256);
            wg_wait<1>();
            uint32_t z = zero;
#pragma unroll
            for (int k = 0; k < 16; k += 2) asm volatile("lop3.b32 %0, %1, %2, %0, 0xA8;" : "+r"(z) : "r"(a[1][k]), "r"(a[1][k + 1]));
            mbar_arrive_cl(rempty, GE + ((i + 3) & 3) * 8 + z);
            mbar_arrive_pred(xempty + ((i + 3) & 3) * 8, l == 0 && i != NRS);
          }
          mbar_wait(xfull + 16, 1);
          wg_wait<0>();
          keep(ga); keep(gb);
#pragma unroll
          for (int i = 0; i < 64; i++) {
            asm volatile("mov.b32 %0, %1;" : "=f"(s[i]) : "f"(ga[i]));
            asm volatile("mov.b32 %0, %1;" : "=f"(o[i]) : "f"(gb[i]));
          }
        } else {
          float ga[64], gb[64];
#pragma unroll
          for (int i = 0; i < 64; i++) {
            asm volatile("mov.b32 %0, %1;" : "=f"(ga[i]) : "f"(s[i]));
            asm volatile("mov.b32 %0, %1;" : "=f"(gb[i]) : "f"(o[i]));
          }
#pragma unroll 1
          for (int i = 0; i < nst; i++) {
            mbar_wait(gfull + (i & 3) * 8, (i >> 2) & 1);
            const uint64_t da = make_desc(base + unit_of(xt, i & 3) + wg * 8192, 16, 1024), db = make_desc(base + unit_of(wt, i & 3), 8192, 1024);
            if (i == nst - 1) bar_sync(2 + wg, 256);
            wg_fence();
#pragma unroll
            for (int kk = 0; kk < 4; kk++) mma256_ss(ga, gb, da + kk * 2, db + kk * 128, kk ? 1 : i);
            wg_commit();
            if (i == nst - 1) bar_arrive(3 - wg, 256);
            wg_wait<1>();
            mbar_arrive_cl(rempty, GE + ((i + 3) & 3) * 8, i != 0);
            PROF(4, tid == 0 && (i & 3) == 0, 40 + (ps - 1) * 4 + i / 4);
          }
          wg_wait<0>();
          keep(ga); keep(gb);
#pragma unroll
          for (int i = 0; i < 64; i++) {
            asm volatile("mov.b32 %0, %1;" : "=f"(s[i]) : "f"(ga[i]));
            asm volatile("mov.b32 %0, %1;" : "=f"(o[i]) : "f"(gb[i]));
          }
        }
        mbar_arrive_cl(rempty, GE + (ps == 2 ? 24 : 8));
        if (ps == 2) break;
      }
      const uint32_t qw = base + wg * 8192, qt = QT >> (16 * ps), at = ps ? AT1 : AT0;
      {
        const uint32_t wt = ps ? WT1 : WT0;
        const uint64_t da0 = make_desc(qw + unit_of(qt, 2), 16, 1024), da1 = make_desc(qw + unit_of(qt, 3), 16, 1024);
        const uint64_t db0 = make_desc(base + unit_of(wt, 2), 8192, 1024), db1 = make_desc(base + unit_of(wt, 3), 8192, 1024);
        mbar_wait(gfull + 16, 1);
        bar_sync(2 + wg, 256);
        wg_fence();
#pragma unroll
        for (int kk = 0; kk < 4; kk++) mma_ss<1>(s, da0 + kk * 2, db0 + kk * 128, 1);
        wg_commit();
        mbar_wait(xfull + 24, 1);
        mbar_wait(gfull + 24, 1);
        wg_fence();
#pragma unroll
        for (int kk = 0; kk < 4; kk++) mma_ss<1>(s, da1 + kk * 2, db1 + kk * 128, 1);
        wg_commit();
        bar_arrive(3 - wg, 256);
        mbar_wait(ps == 0 ? bar_pread : bar_ofree + 8, 0);
        wg_wait<0>();
        keep(s);
        PROF(2, tid == 0, 8 + ps * 8);
        uint32_t q[32];
        pack_p(s, q);
#pragma unroll
        for (int i = 0; i < 4; i++) stmatrix4((qw + unit_of(qt, 0) + frag_offset(warp)) ^ (i << 5), q[4 * i], q[4 * i + 1], q[4 * i + 2], q[4 * i + 3]);
        keep(q);
        bar_sync(2 + wg, 256);
        wg_fence();
#pragma unroll
        for (int kk = 0; kk < 8; kk++) mma_ss<1>(o, (kk < 4 ? da0 : da1) + (kk & 3) * 2, (kk < 4 ? db0 : db1) + UNIT / 16 + (kk & 3) * 128, 1);
        wg_commit();
        mbar_wait(bfull, 0);
        wg_fence();
        const uint64_t dk = make_desc(base + unit_of(at, 0), 16, 1024);
#pragma unroll
        for (int kk = 0; kk < 8; kk++) mma_rs<0>(s, q[4 * kk], q[4 * kk + 1], q[4 * kk + 2], q[4 * kk + 3], dk + (kk >> 2) * 1024 + (kk & 3) * 2, kk != 0);
        wg_commit();
        bar_arrive(3 - wg, 256);
#pragma unroll
        for (int i = 4; i < 8; i++) stmatrix4((qw + unit_of(qt, 1) + frag_offset(warp)) ^ ((i & 3) << 5), q[4 * i], q[4 * i + 1], q[4 * i + 2], q[4 * i + 3]);
        wg_wait<1>();
        keep(o);
        mbar_arrive_cl(rempty, GE + 16);
        mbar_arrive_cl(rempty, GE + 24);
        store_chunk<0>(o, qw + unit_of(qt, 2) + frag_offset(warp));
        store_chunk<1>(o, qw + unit_of(qt, 3) + frag_offset(warp));
        wg_wait<0>();
        keep(s);
        mbar_arrive_cl(rempty, 0);
      }
      PROF(4, tid == 0 && ps == 1, 61);
      float l0 = 0.f, l1 = 0.f;
      auto step = [&](auto odd_c, const int j, uint32_t (&pw)[32], uint32_t (&pr)[32]) {
        constexpr bool ODD = decltype(odd_c)::value;
        const bool first = !ODD && (j & 2) == 0, last = ODD && j == 7;
        const uint32_t ph = (j >> 1) & 1;
        float i0, i1, a0, a1;
        const bool so = !ODD && j == 4;
        if (so) { i0 = inv_quad_sum(l0); i1 = inv_quad_sum(l1); l0 = 0.f; l1 = 0.f; }
        bool redo = !ODD && (j | ps) == 0;
        while (true) {
          if (redo) {
            float m0 = fmaxf(s[0], s[1]), m1 = fmaxf(s[2], s[3]);
#pragma unroll
            for (int i = 1; i < 16; i++) { m0 = fmaxf(m0, fmaxf(s[4 * i], s[4 * i + 1])); m1 = fmaxf(m1, fmaxf(s[4 * i + 2], s[4 * i + 3])); }
            m0 = fmaxf(m0, __shfl_xor_sync(0xffffffffu, m0, 1)); m1 = fmaxf(m1, __shfl_xor_sync(0xffffffffu, m1, 1));
            m0 = fmaxf(m0, __shfl_xor_sync(0xffffffffu, m0, 2)); m1 = fmaxf(m1, __shfl_xor_sync(0xffffffffu, m1, 2));
            m0 *= SCL2; m1 *= SCL2;
            if (!first) {
              m0 = fmaxf(m0, f0); m1 = fmaxf(m1, f1);
              const float c0 = ex2(f0 - m0), c1 = ex2(f1 - m1);
              l0 *= c0; l1 *= c1;
              wg_wait<0>();
              keep(o);
#pragma unroll
              for (int i = 0; i < 16; i++) { o[4 * i] *= c0; o[4 * i + 1] *= c0; o[4 * i + 2] *= c1; o[4 * i + 3] *= c1; }
            }
            f0 = m0; f1 = m1;
          }
          float b0 = 0.f, b1 = 0.f;
          a0 = 0.f; a1 = 0.f;
#pragma unroll
          for (int i = 0; i < 16; i++) {
            const float e0 = ex2(fmaf(s[4 * i], SCL2, -f0)), e1 = ex2(fmaf(s[4 * i + 1], SCL2, -f0));
            const float e2 = ex2(fmaf(s[4 * i + 2], SCL2, -f1)), e3 = ex2(fmaf(s[4 * i + 3], SCL2, -f1));
            a0 += e0; b0 += e1; a1 += e2; b1 += e3;
            pw[2 * i] = pack_bf(e0, e1); pw[2 * i + 1] = pack_bf(e2, e3);
            if (i == VREL) {
#pragma unroll
              for (int k = 0; k < 2 * VREL + 2; k++) asm volatile("" : "+r"(pw[k])::"memory");
              mbar_wait(bar_mod, 0);
              wg_wait<0>();
              mbar_arrive_cl(rempty, ODD ? 16 : 0, !redo && (ODD || j));
#pragma unroll
              for (int k = 4 * VREL + 4; k < 64; k++) asm volatile("" : "+f"(s[k])::"memory");
            }
          }
          a0 += b0; a1 += b1;
          if (redo) break;
          redo = __any_sync(0xffffffffu, !(a0 + a1 < 0x1p90f) || (!ODD && fminf(a0, a1) < (first ? 0x1p-90f : 0.f)));
          if (!redo) break;
        }
        l0 += a0; l1 += a1;
        keep(pw);
        keep(o);
        if (so) store_chunk<0>(o, i0, i1, qw + unit_of(qt, 0) + frag_offset(warp));
        keep(o);
        if (j == (ODD ? 5 : 0)) { fence_async_smem(); if (ODD) mbar_arrive(bar_ofull + wg * 8); }
        mbar_wait(bfull + (ODD ? 24 : 8), ph);
        bar_sync(2 + wg, 256);
        if (!last) {
          const uint32_t qn = qt >> (j >= 3 ? 8 : 0);
          wg_fence();
          issue_qk(s, qw + unit_of(qn, 0), qw + unit_of(qn, 1), base + unit_of(at, ODD ? 3 : 1));
          wg_commit();
          mbar_wait(bfull + (ODD ? 0 : 16), ODD ? ph ^ 1 : ph);
        }
        if (so) { store_chunk<1>(o, i0, i1, qw + unit_of(qt, 1) + frag_offset(warp)); keep(o); }
        wg_fence();
        issue_pv(o, pw, base + unit_of(at, ODD ? (last ? 3 : 0) : 2), !first);
        wg_commit();
        bar_arrive(3 - wg, 256);
        wg_wait<1>();
        keep(s);
        mbar_arrive_cl(rempty, ODD ? 24 : 8, !last);
        PROF(4, tid == 0 && ps == 1, 51 + j);
      };
      uint32_t pa[32], pb[32];
#pragma unroll 1
      for (int j = 0; j < 8; j += 2) {
        step(std::false_type{}, j, pa, pb);
        step(std::true_type{}, j + 1, pb, pa);
      }
      {
        const float i0 = inv_quad_sum(l0), i1 = inv_quad_sum(l1);
        wg_wait<0>();
        keep(o);
        mbar_arrive_cl(rempty, 24);
        store_chunk<0>(o, i0, i1, qw + unit_of(qt, 2) + frag_offset(warp));
        store_chunk<1>(o, i0, i1, qw + unit_of(qt, 3) + frag_offset(warp));
        fence_async_smem();
        mbar_arrive(bar_ofull + 16 + wg * 8);
      }
      PROF(2, tid == 0, 10 + ps * 8);
    }

    const int ln = fresh_lane(), g = ln >> 2, tq = ln & 3, ct = warp * 32 + ln;
    const bool lane0 = ln == 0;
    const int lrow0 = warp * 16 + g;
    const int grow0 = rb * 128 + lrow0;
    const uint32_t res = base + OFF_RES, trow = res + wg * 8192 + frag_offset(warp);
    uint32_t xr[32];
    uint4 sv[4], own;
    uint32_t* const sg = g_stats + (rb * 8 + warp) * 512 + g * 4;
    uint32_t* sp[4];
#pragma unroll
    for (int k = 0; k < 4; k++) sp[k] = sg + (tq & 1) * 32 + (((tq >> 1) ^ (cj >> 2)) * 4 + (k ^ (cj & 3))) * 64;
    {
      const uint64_t da = make_desc(base + wg * 8192, 16, 1024), db = make_desc(base, 8192, 1024);
      constexpr int U = UNIT / 16;
#define HALF_STAGE(acc, xu, wu) _Pragma("unroll") for (int kk = 0; kk < 4; kk++) mma_ss<1>(acc, da + (xu) * U + kk * 2, db + (wu) * U + kk * 128, 1)
      PROF(10, ct == PT, 19); STAMP(0);
      cluster_arrive();
      mbar_wait(gfull, 1);
      mbar_wait(gfull + 8, 1);
      bar_sync(2 + wg, 256);
      wg_fence();
      HALF_STAGE(o, 7, 1);
      HALF_STAGE(o, 8, 3);
      wg_commit();
      STAMP(16);
      mbar_wait(gfull + 16, 1);
      STAMP(17);
      wg_fence();
      HALF_STAGE(o, 6, 11);
      wg_commit();
      bar_arrive(3 - wg, 256);
      mbar_wait(bar_par, 0);
      uint32_t* xo = g_xch + ((size_t)b * 8 * 256 + ct) * 4;
      const uint32_t* xi = g_xch + ((size_t)(b ^ 2) * 8 * 256 + ct) * 4;
      const uint32_t par1 = (~lds1(par + PAR_CONST + 4) & 1) << 16;
      wg_wait<1>();
      mbar_arrive_pred(bar_rel, lane0);
      wg_wait<0>();
      keep(o);
      mbar_arrive_pred(bar_ring, lane0);
      PROF(8, ct == PT, 20); STAMP(1);
#define SEND(i) st_b128(xo + (i) * 1024, (pack_bf(o[8 * (i)], o[8 * (i) + 1]) & ~0x10000u) | par1, pack_bf(o[8 * (i) + 2], o[8 * (i) + 3]), \
                        pack_bf(o[8 * (i) + 4], o[8 * (i) + 5]), pack_bf(o[8 * (i) + 6], o[8 * (i) + 7]))
#pragma unroll
      for (int i = 0; i < NS1; i++) SEND(i);
      PROF(8, ct == PT, 21); STAMP(2);
      bar_sync(2 + wg, 256);
      wg_fence();
      HALF_STAGE(s, 7, 0);
      HALF_STAGE(s, 8, 2);
      HALF_STAGE(s, 6, 10);
      wg_commit();
      bar_arrive(3 - wg, 256);
      STAMP(18);
      mbar_wait(gfull + 24, 1);
#pragma unroll
      for (int i = NS1; i < 8; i++) SEND(i);
      uint4 v[8];
      STAMP(19);
      mbar_wait(bar_xres, 0);
      wg_wait<0>();
      mbar_arrive_pred(bar_ring + 8, lane0);
      bar_sync(2 + wg, 256);
      STAMP(20);
#pragma unroll
      for (int i = 0; i < LD2; i++) v[i] = ld_b128(xi + i * 1024);
      mbar_wait(bar_xres, 0);
      wg_fence();
      HALF_STAGE(s, 9, 4);
      wg_commit();
      mbar_wait(bar_rx, 0);
      wg_fence();
      HALF_STAGE(s, 1, 5);
      wg_commit();
      bar_arrive(3 - wg, 256);
      STAMP(21);
#pragma unroll
      for (int i = LD2; i < 8; i++) v[i] = ld_b128(xi + i * 1024);
      mbar_wait(bar_xres, 0);
      wg_wait<0>();
      keep(s);
      mbar_arrive_pred(bar_ring + 16, lane0);
      PROF(10, ct == PT, 23); STAMP(4);
#pragma unroll
      for (int i = 0; i < 16; i += 2) ldmatrix4((trow ^ ((i & 7) << 4)) + (i >> 3) * 16384, xr[2 * i], xr[2 * i + 1], xr[2 * i + 2], xr[2 * i + 3]);
      uint32_t ga[16];
      uint4 bw[8];
#pragma unroll
      for (int i = 0; i < 8; i++) {
        if (!(i & 1)) {
          const uint4 t = lds4(par + PAR_SINK + i * 32 + tq * 16);
          ga[2 * i] = t.x; ga[2 * i + 1] = t.y; ga[2 * i + 2] = t.z; ga[2 * i + 3] = t.w;
        }
        bw[i] = lds4(par + PAR_T1 + i * 64 + tq * 16);
        if (!(g & 1)) { bw[i].x = 0x3f803f80u; bw[i].y = 0x3f803f80u; }
      }
      uint32_t pk[32];
      pack_p(s, pk);
      keep(pk);
      {
        uint32_t n = 0, miss;
        do {
          miss = 0;
#pragma unroll
          for (int i = 0; i < 8; i++) miss |= v[i].x ^ par1;
          miss = __any_sync(0xffffffffu, miss & 0x10000u);
          if (miss) {
#pragma unroll
            for (int i = 0; i < 8; i++)
              asm volatile("{ .reg .pred p; .reg .b32 t; xor.b32 t, %0, %5; and.b32 t, t, 0x10000; setp.ne.u32 p, t, 0;\n"
                           "@p ld.relaxed.gpu.global.v4.u32 {%0, %1, %2, %3}, [%4]; }"
                           : "+r"(v[i].x), "+r"(v[i].y), "+r"(v[i].z), "+r"(v[i].w) : "l"(xi + i * 1024), "r"(par1) : "memory");
          }
          watchdog(n);
        } while (miss);
      }
      PROF(8, ct == PT, 22); STAMP(3);
      float ds[4] = {0.f, 0.f, 0.f, 0.f}, dl[4] = {0.f, 0.f, 0.f, 0.f}, q0[4] = {0.f, 0.f, 0.f, 0.f}, q1[4] = {0.f, 0.f, 0.f, 0.f};
#pragma unroll
      for (int i = 0; i < 8; i++) {
        const uint32_t u0 = hfma2(ga[2 * i], hadd2(pk[4 * i], v[i].x & ~0x10000u), xr[4 * i]);
        const uint32_t u1 = hfma2(ga[2 * i], hadd2(pk[4 * i + 1], v[i].y), xr[4 * i + 1]);
        const uint32_t u2 = hfma2(ga[2 * i + 1], hadd2(pk[4 * i + 2], v[i].z), xr[4 * i + 2]);
        const uint32_t u3 = hfma2(ga[2 * i + 1], hadd2(pk[4 * i + 3], v[i].w), xr[4 * i + 3]);
        xr[4 * i] = u0; xr[4 * i + 1] = u1; xr[4 * i + 2] = u2; xr[4 * i + 3] = u3;
        mma16816(ds, u0, u1, u2, u3, bw[i].x, bw[i].y);
        mma16816(dl, u0, u1, u2, u3, bw[i].z, bw[i].w);
        mma16816(q0, u0, u1, u2, u3, u0, u2);
        mma16816(q1, u0, u1, u2, u3, u1, u3);
      }
      const float sqa = (g & 1) ? q0[1] : q0[0], sqb = (g & 1) ? q1[3] : q1[2], dta = ds[1] + dl[1], dtb = ds[3] + dl[3];
      if (tq == (g >> 1)) {
        st_b128(sg + cj * 64, __float_as_uint(ds[0]), __float_as_uint(sqa), __float_as_uint(dta), tag);
        st_b128(sg + cj * 64 + 32, __float_as_uint(ds[2]), __float_as_uint(sqb), __float_as_uint(dtb), tag);
      }
#pragma unroll
      for (int k = 0; k < 4; k++) sv[k] = ld_b128(sp[k]);
      mbar_wait(bar_xres, 0);
      const float sqc = __shfl_sync(0xffffffffu, sqa, g * 4 + (g >> 1)), sqd = __shfl_sync(0xffffffffu, sqb, g * 4 + (g >> 1));
      own = (tq & 1) ? make_uint4(__float_as_uint(ds[2]), __float_as_uint(sqd), __float_as_uint(dtb), tag)
                     : make_uint4(__float_as_uint(ds[0]), __float_as_uint(sqc), __float_as_uint(dta), tag);
    }
    PROF(8, ct == PT, 29); STAMP(5);
    uint32_t mm, ih, il;
    float rbest;
    uint32_t wf[128];
    const uint32_t frow = (ln & 7) + (ln >> 4) * 8;
    const uint32_t wfo = base + (warp & 1) * 8192 + frow * 64 + ((((ln >> 3) & 1) ^ ((frow >> 1) & 3)) << 4);
#define LOAD_WF(m) _Pragma("unroll") for (int f = 0; f < 16; f++) {                                                   \
      const int r = ((f >> 1) * 4 + (m) * 2 + (f & 1)) * 4;                                                           \
      ldmatrix4t(((wfo + unit_of((m) ? FT_U : FT_G, warp >> 1)) ^ ((f & 1) * 32)) + (f >> 1) * 1024, wf[r], wf[r + 1], wf[r + 2], wf[r + 3]); \
    }
    bool early;
    {
#pragma unroll
      for (int i = 0; i < 16; i += 2) stmatrix4((trow ^ ((i & 7) << 4)) + (i >> 3) * 16384, xr[2 * i], xr[2 * i + 1], xr[2 * i + 2], xr[2 * i + 3]);
      const uint4 cst = lds4(par + PAR_CONST);
      const float A1 = __uint_as_float(cst.x), A2 = __uint_as_float(cst.z);
      uint32_t n = 0;
      early = false;
#pragma unroll 1
      while (true) {
        if (!early && (b >= NFFN || __all_sync(0xffffffffu, mbar_test(bar_box + (warp >> 1) * 8, 0)))) {
          early = true;
          LOAD_WF(0);
          __syncwarp();
          mbar_arrive_pred(bar_gate, lane0);
        }
        uint32_t miss;
        asm volatile("{ .reg .pred p0, p1, p2, p3; .reg .b64 u, v; .reg .b128 w;\n"
                     "setp.ge.u32 p0, %22, 2; setp.ne.and.u32 p0, %4, %21, p0; setp.ne.u32 p1, %8, %21; setp.ne.u32 p2, %12, %21; setp.ne.u32 p3, %16, %21;\n"
                     "@p0 ld.relaxed.gpu.global.v4.u32 {%1, %2, %3, %4}, [%17];\n"
                     "@p1 ld.relaxed.gpu.global.v4.u32 {%5, %6, %7, %8}, [%18];\n"
                     "@p2 ld.relaxed.gpu.global.v4.u32 {%9, %10, %11, %12}, [%19];\n"
                     "@p3 ld.relaxed.gpu.global.v4.u32 {%13, %14, %15, %16}, [%20];\n"
                     "or.pred p0, p0, p1; or.pred p2, p2, p3; or.pred p0, p0, p2; vote.sync.any.pred p0, p0, 0xffffffff; selp.u32 %0, 1, 0, p0; }"
                     : "=r"(miss), "+r"(sv[0].x), "+r"(sv[0].y), "+r"(sv[0].z), "+r"(sv[0].w), "+r"(sv[1].x), "+r"(sv[1].y), "+r"(sv[1].z), "+r"(sv[1].w),
                       "+r"(sv[2].x), "+r"(sv[2].y), "+r"(sv[2].z), "+r"(sv[2].w), "+r"(sv[3].x), "+r"(sv[3].y), "+r"(sv[3].z), "+r"(sv[3].w)
                     : "l"(sp[0]), "l"(sp[1]), "l"(sp[2]), "l"(sp[3]), "r"(tag), "r"(tq) : "memory");
        if (!miss) break;
        watchdog(n);
      }
      const uint4 v0 = tq < 2 ? own : sv[0], v1 = sv[1], v2 = sv[2], v3 = sv[3];
      PROF(8, ct == PT, 30); STAMP(6);
      float su = (__uint_as_float(v0.x) + __uint_as_float(v1.x)) + (__uint_as_float(v2.x) + __uint_as_float(v3.x));
      float sq = (__uint_as_float(v0.y) + __uint_as_float(v1.y)) + (__uint_as_float(v2.y) + __uint_as_float(v3.y));
      float dt = (__uint_as_float(v0.z) + __uint_as_float(v1.z)) + (__uint_as_float(v2.z) + __uint_as_float(v3.z));
      su += __shfl_xor_sync(0xffffffffu, su, 2); sq += __shfl_xor_sync(0xffffffffu, sq, 2); dt += __shfl_xor_sync(0xffffffffu, dt, 2);
      const float m = su * (1.f / DM);
      float mb, sd;
      ln_scalars(m, fmaxf(sq * (1.f / DM) - m * m, 0.f), mb, sd);
      const float inv = rcp(sd);
      rbest = (dt - mb * A1) * inv + A2;
      mm = pack_bf(mb, mb);
      ih = pack_bf(inv, inv);
      const float lo = inv - bf_lo(ih);
      il = pack_bf(lo, lo);
    }
    int ibest;
    {
      const uint32_t bits = __float_as_uint(rbest);
      const uint32_t key = (((int)bits < 0 ? ~bits : bits | 0x80000000u) & ~0x1ffu) | ((127 - lrow0 - (tq & 1) * 8) << 2) | tag;
      sts1(par + PAR_RED + warp * 4, __reduce_max_sync(0xffffffffu, key));
      PROF(8, ct == PT, 38); STAMP(7);
      bar_sync(1, 256);
      const uint4 ka = lds4(par + PAR_RED), kb = lds4(par + PAR_RED + 16);
      const uint32_t k2 = max(max(max(ka.x, ka.y), max(ka.z, ka.w)), max(max(kb.x, kb.y), max(kb.z, kb.w)));
      if (ct < CR && cj == 0) st_relaxed(g_cand + ct * 512 + rb * CS, k2);
      ibest = 127 - ((k2 >> 2) & 127);
    }
    PROF(8, ct == PT, 39); STAMP(8);
    if ((ibest >> 4) == warp) {
      const int src = (ibest & 7) * 4 + ((ibest >> 3) & 1), ch = g * 2;
      const uint32_t cm = __shfl_sync(0xffffffffu, mm, src), ch_ = __shfl_sync(0xffffffffu, ih, src), cl = __shfl_sync(0xffffffffu, il, src);
      const uint32_t xa = res + (ch >> 3) * 16384 + ibest * 128 + (((ch & 7) ^ (ibest & 7)) << 4) + tq * 4;
      const uint32_t x0 = lds1(xa), x1 = lds1(xa ^ 16);
      const uint2 p0 = lds2(par + PAR_T2 + ch * 64 + tq * 16), p1 = lds2(par + PAR_T2 + ch * 64 + 64 + tq * 16);
      uint32_t* dst = g_row + rb * 2 * DM + cj * 128 + ln * 4;
      st_pairs(dst, ln_mod(x0, cm, ch_, cl, p0.x, p0.y), ln_mod(x1, cm, ch_, cl, p1.x, p1.y), tag);
      st_pairs(dst + DM, x0, x1, tag);
      __syncwarp();
    }
    PROF(8, ct == PT, 37); STAMP(9);
    uint32_t wd[64];
    const uint32_t wda = base + unit_of(FT_D, warp >> 1) + (warp & 1) * 8192 + frow * 128 + ((((ln >> 3) & 1) ^ (ln & 7)) << 4);
#define LOAD_WD(f) ldmatrix4t((wda ^ ((((f) >> 1) & 3) * 32)) + ((f) >> 3) * 4096 + ((f) & 1) * 2048, wd[4 * (f)], wd[4 * (f) + 1], wd[4 * (f) + 2], wd[4 * (f) + 3])
    if (!early) {
      if (b < NFFN) mbar_wait(bar_box + (warp >> 1) * 8, 0);
      LOAD_WF(0);
      __syncwarp();
      mbar_arrive_pred(bar_gate, lane0);
    }
    if (b < NFFN) {
      const uint32_t own = base + unit_of(FT_G, warp >> 1) + (warp & 1) * 8192;
      mbar_wait(bar_box + (4 + (warp >> 1)) * 8, 0);
      LOAD_WF(1);
      uint32_t* const ydst = ypart_slot(b, warp * 16 + (tq & 1) * 8 + g);
      PROF(8, ct == PT, 31); STAMP(10);
      bool wdok;
      {
        uint32_t n = 0;
        while (!(wdok = __all_sync(0xffffffffu, mbar_test(bar_box + (8 + (warp >> 1)) * 8, 0))) && !__all_sync(0xffffffffu, mbar_test(bar_sel, 0))) watchdog(n);
      }
      if (wdok) {
#pragma unroll
        for (int f = 0; f < 16; f++) LOAD_WD(f);
      }
      STAMP(11);
      mbar_wait(bar_sel, 0);
      PROF(8, ct == PT, 33); STAMP(12);
      float d[8][4];
#pragma unroll
      for (int i = 0; i < 4; i++) { d[i][0] = 0.f; d[i][1] = 0.f; d[i][2] = 0.f; d[i][3] = 0.f; }
#pragma unroll
      for (int ks = 0; ks < 8; ks++) {
        const uint2 hb = lds2(own + 256 + ks * 32 + tq * 8);
#pragma unroll
        for (int mt = 0; mt < 4; mt++) {
          const int r = ks * 16 + mt * 4;
          mma16816(d[mt], wf[r], wf[r + 1], wf[r + 2], wf[r + 3], hb.x, hb.y);
        }
      }
      sts2(own + (tq * 8 + g) * 8, __float_as_uint((tq & 2) ? ((tq & 1) ? d[1][2] : d[1][0]) : ((tq & 1) ? d[0][2] : d[0][0])),
           __float_as_uint((tq & 2) ? ((tq & 1) ? d[3][2] : d[3][0]) : ((tq & 1) ? d[2][2] : d[2][0])));
      bar_sync(1, 256);
      uint32_t ab[4];
      {
        float G = 0.f, U = 0.f;
        uint2 pv[8];
#pragma unroll
        for (int w8 = 0; w8 < 8; w8++) pv[w8] = lds2(base + ln * 8 + ((FT_G >> (w8 >> 1) * 4) & 15) * UNIT + (w8 & 1) * 8192);
#pragma unroll
        for (int w8 = 0; w8 < 8; w8 += 2) {
          G += __uint_as_float(pv[w8].x) + __uint_as_float(pv[w8 + 1].x);
          U += __uint_as_float(pv[w8].y) + __uint_as_float(pv[w8 + 1].y);
        }
        const float act = rbf(silu_f(rbf(G))) * rbf(U);
        const uint32_t pk = pack_bf(act, __shfl_down_sync(0xffffffffu, act, 1));
#pragma unroll
        for (int i = 0; i < 4; i++) ab[i] = __shfl_sync(0xffffffffu, pk, i * 8 + tq * 2);
      }
      if (!wdok) {
        mbar_wait(bar_box + (8 + (warp >> 1)) * 8, 0);
#pragma unroll
        for (int f = 0; f < 16; f++) LOAD_WD(f);
      }
      PROF(8, ct == PT, 34); STAMP(13);
#pragma unroll
      for (int mt = 0; mt < 8; mt++) {
        d[mt][0] = 0.f; d[mt][1] = 0.f; d[mt][2] = 0.f; d[mt][3] = 0.f;
        mma16816(d[mt], wd[mt * 8], wd[mt * 8 + 1], wd[mt * 8 + 2], wd[mt * 8 + 3], ab[0], ab[1]);
        mma16816(d[mt], wd[mt * 8 + 4], wd[mt * 8 + 5], wd[mt * 8 + 6], wd[mt * 8 + 7], ab[2], ab[3]);
      }
      uint32_t yw[4];
#pragma unroll
      for (int i = 0; i < 4; i++) yw[i] = (tq & 1) ? pack_bf(d[2 * i][2], d[2 * i + 1][2]) : pack_bf(d[2 * i][0], d[2 * i + 1][0]);
      if (tq < 2) st_b128(ydst, (yw[0] & ~1u) | (tag & 1), (yw[1] & ~1u) | (tag >> 1), yw[2], yw[3]);
      PROF(8, ct == PT, 35); STAMP(14);
    }
    mbar_wait(bar_sel, 0);
    mbar_arrive_pred(bar_win, ct == 0);
    const int iwin = lds1(par + PAR_CONST + 60) & 0x7ff;
    const bool cand = (iwin >> 4) == rb * 8 + warp;
    {
      const uint32_t mm0 = __shfl_sync(0xffffffffu, mm, ln & ~1), mm1 = __shfl_sync(0xffffffffu, mm, ln | 1);
      const uint32_t ih0 = __shfl_sync(0xffffffffu, ih, ln & ~1), ih1 = __shfl_sync(0xffffffffu, ih, ln | 1);
      const uint32_t il0 = __shfl_sync(0xffffffffu, il, ln & ~1), il1 = __shfl_sync(0xffffffffu, il, ln | 1);
#pragma unroll 1
      for (int hf = 0; hf < 2; hf++) {
        uint32_t x[16];
#pragma unroll
        for (int i = 0; i < 8; i += 2) ldmatrix4((trow ^ (i << 4)) + hf * 16384, x[2 * i], x[2 * i + 1], x[2 * i + 2], x[2 * i + 3]);
#pragma unroll
        for (int i = 0; i < 8; i++) {
          const uint4 pv = lds4(par + PAR_T2 + (hf * 8 + i) * 64 + tq * 16);
          x[2 * i] = hfma2(hfma2(ln_norm(x[2 * i], mm0, ih0, il0), pv.x, pv.y), pv.z, x[2 * i]);
          x[2 * i + 1] = hfma2(hfma2(ln_norm(x[2 * i + 1], mm1, ih1, il1), pv.x, pv.y), pv.z, x[2 * i + 1]);
        }
#pragma unroll
        for (int i = 0; i < 8; i += 2) stmatrix4((trow ^ (i << 4)) + hf * 16384, x[2 * i], x[2 * i + 1], x[2 * i + 2], x[2 * i + 3]);
        if (!cand) fence_async_smem();
        __syncwarp();
        if (!cand && elect_one()) {
          tma2d_store(&maps.out, res + hf * 16384 + warp * 2048, cj * 128 + hf * 64, rb * 128 + warp * 16);
          asm volatile("cp.async.bulk.commit_group;" ::: "memory");
        }
      }
    }
    if (cand) {
      const int wrow0 = warp * 16;
#pragma unroll 2
      for (int p = 0; p < 8; p++) {
        const int row = 2 * p + (ln >> 4), ch = ln & 15;
        const uint4 v = lds4(res + (ch >> 3) * 16384 + (wrow0 + row) * 128 + (((ch & 7) ^ (row & 7)) << 4));
        if (rb * 128 + wrow0 + row != iwin) *reinterpret_cast<uint4*>(P.out + (size_t)(rb * 128 + wrow0 + row) * DM + cj * 128 + ch * 8) = v;
      }
    }
    asm volatile("cp.async.bulk.wait_group.read 0;" ::: "memory");
    PROF(8, ct == PT, 11); STAMP(15);
    cluster_wait();
  }
}

typedef CUresult (*EncodeFn)(CUtensorMap*, CUtensorMapDataType, cuuint32_t, void*, const cuuint64_t*, const cuuint64_t*,
                             const cuuint32_t*, const cuuint32_t*, CUtensorMapInterleave, CUtensorMapSwizzle,
                             CUtensorMapL2promotion, CUtensorMapFloatOOBfill);

void map2d(EncodeFn enc, CUtensorMap* m, const void* p, uint64_t rows, uint64_t cols, uint32_t brows) {
  cuuint64_t dims[2] = {cols, rows}, strides[1] = {cols * 2};
  cuuint32_t box[2] = {64, brows}, es[2] = {1, 1};
  enc(m, CU_TENSOR_MAP_DATA_TYPE_BFLOAT16, 2, const_cast<void*>(p), dims, strides, box, es, CU_TENSOR_MAP_INTERLEAVE_NONE,
      CU_TENSOR_MAP_SWIZZLE_128B, CU_TENSOR_MAP_L2_PROMOTION_L2_256B, CU_TENSOR_MAP_FLOAT_OOB_FILL_NONE);
}
void map2d_narrow(EncodeFn enc, CUtensorMap* m, const void* p, uint64_t rows, uint64_t cols, uint32_t brows) {
  cuuint64_t dims[2] = {cols, rows}, strides[1] = {cols * 2};
  cuuint32_t box[2] = {32, brows}, es[2] = {1, 1};
  enc(m, CU_TENSOR_MAP_DATA_TYPE_BFLOAT16, 2, const_cast<void*>(p), dims, strides, box, es, CU_TENSOR_MAP_INTERLEAVE_NONE,
      CU_TENSOR_MAP_SWIZZLE_64B, CU_TENSOR_MAP_L2_PROMOTION_L2_64B, CU_TENSOR_MAP_FLOAT_OOB_FILL_NONE);
}
void map3d(EncodeFn enc, CUtensorMap* m, const void* p, uint64_t rows, uint64_t cols, uint32_t brows, uint32_t nch) {
  cuuint64_t dims[3] = {64, rows, cols / 64}, strides[2] = {cols * 2, 128};
  cuuint32_t box[3] = {64, brows, nch}, es[3] = {1, 1, 1};
  enc(m, CU_TENSOR_MAP_DATA_TYPE_BFLOAT16, 3, const_cast<void*>(p), dims, strides, box, es, CU_TENSOR_MAP_INTERLEAVE_NONE,
      CU_TENSOR_MAP_SWIZZLE_128B, CU_TENSOR_MAP_L2_PROMOTION_L2_256B, CU_TENSOR_MAP_FLOAT_OOB_FILL_NONE);
}

}

extern "C" void kernel_launch(void* const* d_in, const int* in_sizes, int n_in, void* d_out, int out_size) {
  (void)in_sizes; (void)n_in; (void)out_size;
  static EncodeFn enc = nullptr;
  if (!enc) {
    void* fn = nullptr;
    cudaDriverEntryPointQueryResult st;
    cudaGetDriverEntryPoint("cuTensorMapEncodeTiled", &fn, cudaEnableDefault, &st);
    enc = (EncodeFn)fn;
    cudaFuncSetAttribute(fused_kernel, cudaFuncAttributeMaxDynamicSharedMemorySize, SMEM_BYTES);
  }
  Maps maps;
  map2d(enc, &maps.x, d_in[0], SEQ, DM, 128);
  map2d(enc, &maps.out, d_out, SEQ, DM, 16);
  map3d(enc, &maps.wq, d_in[3], DM, NQ, 64, 2);
  map3d(enc, &maps.k, d_in[1], 4 * SK, 128, 128, 1);
  map3d(enc, &maps.v, d_in[2], 4 * SK, 128, 128, 1);
  map3d(enc, &maps.wo, d_in[4], NQ, DM, 64, 2);
  map2d_narrow(enc, &maps.wg, d_in[7], DM, FF, 256);
  map2d_narrow(enc, &maps.wu, d_in[8], DM, FF, 256);
  map3d(enc, &maps.wd, d_in[9], FF, DM, 32, 4);
  map2d_narrow(enc, &maps.wm, d_in[11], DM, NMOD, 256);
  Ptrs p;
  p.x = (const __nv_bfloat16*)d_in[0];
  p.w_r = (const __nv_bfloat16*)d_in[6];
  p.w_gate = (const __nv_bfloat16*)d_in[7];
  p.w_up = (const __nv_bfloat16*)d_in[8];
  p.w_down = (const __nv_bfloat16*)d_in[9];
  p.c = (const __nv_bfloat16*)d_in[10];
  p.w_mod = (const __nv_bfloat16*)d_in[11];
  p.out = (__nv_bfloat16*)d_out;
  fused_kernel<<<NMAIN + NHELP, 384, SMEM_BYTES>>>(maps, p);
}
```

```cpp
#include <cuda_runtime.h>
#include <cuda_bf16.h>
#include <cuda.h>
#include <stdint.h>
#include <type_traits>

#define HD 2
#define HDX 2
#define NRS 8
#define OSL 900
#define OSL2 400
#define RSL 40
#define ZM 1
#define VREL 5
#define OPS 8192
#define ODS1 5
#define ODS 7
#define PG0 15
#define WB 2
#define WN 20
#define HU 32
#define RES0 17
#define RES1 20
#define GOST 20
#define NS1 5
#define LD2 4
#define FPACE0 2
#define FPACE 3
#define CR 8
#define CS 8

namespace {

constexpr int SEQ = 2048, DM = 1024, NQ = 4096, SK = 2048, WIN = 512, FF = 3584, NMOD = 6144;
constexpr int NMAIN = 128, NHELP = 4, NFFN = 112;
constexpr int NSLOT = 4, SLOT_BYTES = 32768, UNIT = 16384, GST_BYTES = 3 * UNIT;
constexpr uint32_t XT1 = 0xDCBA, XT2 = 0x9687;
constexpr uint32_t WT0 = 0xA741, WT1 = 0x7420, WT2 = 0x4A20;
constexpr uint32_t AT0 = WT1, AT1 = WT2;
constexpr uint32_t QT = 0xDC9696DC;
constexpr int OFF_STAGE = 12 * UNIT;
constexpr uint32_t FT_G = 0x07B3, FT_U = 0xA628, FT_D = 0x5149;
constexpr int OFF_RES = 12 * UNIT;
constexpr int OFF_PAR = 14 * UNIT;
constexpr int OFF_BAR = OFF_PAR + 2528;
constexpr int SMEM_BYTES = OFF_BAR + 544;
static_assert(SMEM_BYTES <= 232448, "smem");

constexpr int PAR_T1 = 0;
constexpr int PAR_T2 = 512;
constexpr int PAR_CONST = 1536;
constexpr int PAR_RED = 1600;
constexpr int PAR_SINK = 2176;

struct Maps {
  CUtensorMap x, wq, k, v, wo, wg, wu, wd, wm, out;
};
struct Ptrs {
  const __nv_bfloat16 *x, *w_r, *c, *w_mod, *w_gate, *w_up, *w_down;
  __nv_bfloat16* out;
};

__device__ __align__(1024) uint8_t g_act[16 * 80 * UNIT];
__device__ __align__(128) uint32_t g_mod[NMOD];
__device__ __align__(128) uint32_t g_modp[2 * 2 * DM];
__device__ __align__(128) uint32_t g_ln1[SEQ * 4];
__device__ __align__(128) uint32_t g_cnt_h[16 * 32];
__device__ __align__(128) uint32_t g_cnt_o[128 * 32];
__device__ __align__(128) uint32_t g_xch[NMAIN * 8 * 256 * 4];
__device__ __align__(128) uint32_t g_stats[8 * SEQ * 4];
__device__ __align__(128) uint32_t g_cand[CR * 512];
__device__ __align__(128) uint32_t g_row[16 * 2 * DM];
__device__ __align__(128) uint32_t g_ypart[NMAIN * NFFN * 4];
__device__ __forceinline__ uint32_t* ypart_slot(int writer, int reader) { return g_ypart + (writer * NMAIN + reader) * 4; }
__device__ uint32_t g_epoch;

__device__ __forceinline__ uint32_t fresh_lane() { uint32_t l; asm volatile("mov.u32 %0, %%laneid;" : "=r"(l)); return l; }
__device__ __forceinline__ uint32_t frag_offset(int warp) {
  const uint32_t l = fresh_lane();
  return ((warp & 3) * 16 + (l & 15)) * 128 + (((l >> 4) ^ (l & 7)) << 4);
}
__device__ __forceinline__ bool elect_one() {
  uint32_t p;
  asm volatile("{ .reg .pred q; elect.sync _|q, 0xffffffff; selp.u32 %0, 1, 0, q; }" : "=r"(p));
  return p;
}
__device__ __forceinline__ uint32_t smem_u32(const void* p) { return (uint32_t)__cvta_generic_to_shared(p); }
__device__ __forceinline__ void mbar_init(uint32_t bar, uint32_t cnt) {
  asm volatile("mbarrier.init.shared::cta.b64 [%0], %1;" ::"r"(bar), "r"(cnt) : "memory");
}
__device__ __forceinline__ void mbar_expect_tx(uint32_t bar, uint32_t bytes) {
  asm volatile("mbarrier.arrive.expect_tx.shared::cta.b64 _, [%0], %1;" ::"r"(bar), "r"(bytes) : "memory");
}
__device__ __forceinline__ void mbar_arrive(uint32_t bar) {
  asm volatile("mbarrier.arrive.shared::cta.b64 _, [%0];" ::"r"(bar) : "memory");
}
__device__ __forceinline__ void mbar_arrive_pred(uint32_t bar, bool p) {
  asm volatile("{ .reg .pred p; setp.ne.b32 p, %1, 0; @p mbarrier.arrive.shared::cta.b64 _, [%0]; }" ::"r"(bar), "r"((int)p) : "memory");
}
__device__ __forceinline__ void mbar_arrive_cl(uint32_t bar, uint32_t off, bool p = true) {
  asm volatile("{ .reg .pred p, q; .reg .b32 a; setp.ne.b32 q, %2, 0; setp.ne.and.b32 p, %0, 0, q; add.u32 a, %0, %1; @p mbarrier.arrive.shared::cluster.b64 _, [a]; }"
               ::"r"(bar), "r"(off), "r"((int)p) : "memory");
}
__device__ __forceinline__ uint32_t mapa(uint32_t addr, uint32_t cta) {
  uint32_t r; asm("mapa.shared::cluster.u32 %0, %1, %2;" : "=r"(r) : "r"(addr), "r"(cta)); return r;
}
__device__ __forceinline__ void cluster_arrive() { asm volatile("barrier.cluster.arrive.relaxed.aligned;" ::: "memory"); }
__device__ __forceinline__ void cluster_wait() { asm volatile("barrier.cluster.wait.aligned;" ::: "memory"); }
__device__ __forceinline__ void watchdog(uint32_t& n) {
}
__device__ __forceinline__ void mbar_wait(uint32_t bar, uint32_t parity) {
  asm volatile("{\n.reg .pred p;\nWAIT_%=:\nmbarrier.try_wait.parity.shared::cta.b64 p, [%0], %1;\n@!p bra WAIT_%=;\n}" ::"r"(bar), "r"(parity) : "memory");
}
__device__ __forceinline__ bool mbar_test(uint32_t bar, uint32_t parity) {
  uint32_t ok;
  asm volatile("{\n.reg .pred p;\nmbarrier.test_wait.parity.shared::cta.b64 p, [%1], %2;\nselp.u32 %0, 1, 0, p;\n}" : "=r"(ok) : "r"(bar), "r"(parity) : "memory");
  return ok;
}
__device__ __forceinline__ uint64_t l2_stream() {
  uint64_t f; asm("createpolicy.fractional.L2::evict_first.b64 %0, 1.0;" : "=l"(f)); return f;
}
__device__ __forceinline__ uint64_t l2_normal() {
  uint64_t f; asm("createpolicy.fractional.L2::evict_normal.b64 %0, 1.0;" : "=l"(f)); return f;
}
__device__ __forceinline__ void tma2d(uint32_t dst, const CUtensorMap* m, int c0, int c1, uint32_t bar) {
  asm volatile("cp.async.bulk.tensor.2d.shared::cluster.global.mbarrier::complete_tx::bytes.L2::cache_hint [%0], [%1, {%3, %4}], [%2], %5;"
               ::"r"(dst), "l"(m), "r"(bar), "r"(c0), "r"(c1), "l"(l2_stream()) : "memory");
}
__device__ __forceinline__ void bulk_load(uint32_t dst, const void* src, uint32_t bytes, uint32_t bar) {
  asm volatile("cp.async.bulk.shared::cluster.global.mbarrier::complete_tx::bytes [%0], [%1], %2, [%3];" ::"r"(dst), "l"(src), "r"(bytes), "r"(bar) : "memory");
}
__device__ __forceinline__ void bulk_load_stream(uint32_t dst, const void* src, uint32_t bytes, uint32_t bar, uint64_t pol = l2_stream()) {
  asm volatile("cp.async.bulk.shared::cluster.global.mbarrier::complete_tx::bytes.L2::cache_hint [%0], [%1], %2, [%3], %4;"
               ::"r"(dst), "l"(src), "r"(bytes), "r"(bar), "l"(pol) : "memory");
}
__device__ __forceinline__ void tma2d_store(const CUtensorMap* m, uint32_t src, int c0, int c1) {
  asm volatile("cp.async.bulk.tensor.2d.global.shared::cta.bulk_group [%0, {%2, %3}], [%1];" ::"l"(m), "r"(src), "r"(c0), "r"(c1) : "memory");
}
__device__ __forceinline__ void bulk_store(void* dst, uint32_t src, uint32_t bytes) {
  asm volatile("cp.async.bulk.global.shared::cta.bulk_group [%0], [%1], %2;" ::"l"(dst), "r"(src), "r"(bytes) : "memory");
}
__device__ __forceinline__ int slice_of(int i) { return i + ((i & 7) == 1) - ((i & 7) == 2); }
__device__ __forceinline__ uint32_t unit_of(uint32_t table, uint32_t i) { return ((table >> (i * 4)) & 15) * UNIT; }
__device__ __forceinline__ void tma3d(uint32_t dst, const CUtensorMap* m, int c0, int c1, int c2, uint32_t bar) {
  asm volatile("cp.async.bulk.tensor.3d.shared::cluster.global.mbarrier::complete_tx::bytes.L2::cache_hint [%0], [%1, {%3, %4, %5}], [%2], %6;"
               ::"r"(dst), "l"(m), "r"(bar), "r"(c0), "r"(c1), "r"(c2), "l"(l2_stream()) : "memory");
}
template <bool STREAM>
__device__ __forceinline__ void tma3d_mc(uint32_t dst, const CUtensorMap* m, int c0, int c1, int c2, uint32_t bar) {
  if (STREAM)
    asm volatile("cp.async.bulk.tensor.3d.shared::cluster.global.mbarrier::complete_tx::bytes.multicast::cluster.L2::cache_hint [%0], [%1, {%3, %4, %5}], [%2], %6, %7;"
                 ::"r"(dst), "l"(m), "r"(bar), "r"(c0), "r"(c1), "r"(c2), "h"((uint16_t)3), "l"(l2_stream()) : "memory");
  else
    asm volatile("cp.async.bulk.tensor.3d.shared::cluster.global.mbarrier::complete_tx::bytes.multicast::cluster [%0], [%1, {%3, %4, %5}], [%2], %6;"
                 ::"r"(dst), "l"(m), "r"(bar), "r"(c0), "r"(c1), "r"(c2), "h"((uint16_t)3) : "memory");
}
__device__ __forceinline__ void prefetch_map(const CUtensorMap* m) {
  asm volatile("prefetch.tensormap [%0];" ::"l"(m) : "memory");
}
__device__ __forceinline__ void fence_async() { asm volatile("fence.proxy.async.global;" ::: "memory"); }
__device__ __forceinline__ void fence_async_smem() { asm volatile("fence.proxy.async.shared::cta;" ::: "memory"); }
__device__ __forceinline__ void bar_sync(int id, int n) { asm volatile("bar.sync %0, %1;" ::"r"(id), "r"(n) : "memory"); }
__device__ __forceinline__ void bar_arrive(int id, int n) { asm volatile("bar.arrive %0, %1;" ::"r"(id), "r"(n) : "memory"); }
__device__ __forceinline__ void wg_fence() { asm volatile("wgmma.fence.sync.aligned;" ::: "memory"); }
__device__ __forceinline__ void wg_commit() { asm volatile("wgmma.commit_group.sync.aligned;" ::: "memory"); }
template <int N> __device__ __forceinline__ void wg_wait() { asm volatile("wgmma.wait_group.sync.aligned %0;" ::"n"(N) : "memory"); }
__device__ __forceinline__ uint64_t make_desc(uint32_t addr, uint32_t lbo, uint32_t sbo) {
  return (uint64_t)((addr & 0x3FFFF) >> 4) | ((uint64_t)(lbo >> 4) << 16) | ((uint64_t)(sbo >> 4) << 32) | (1ull << 62);
}
__device__ __forceinline__ uint32_t ld_relaxed(const uint32_t* p) {
  uint32_t v; asm volatile("ld.relaxed.gpu.global.u32 %0, [%1];" : "=r"(v) : "l"(p) : "memory"); return v;
}
__device__ __forceinline__ uint32_t ld_acquire(const uint32_t* p) {
  uint32_t v; asm volatile("ld.acquire.gpu.global.u32 %0, [%1];" : "=r"(v) : "l"(p) : "memory"); return v;
}
__device__ __forceinline__ uint4 ld_relaxed4(const uint32_t* p) {
  uint4 v; asm volatile("ld.relaxed.gpu.global.v4.u32 {%0,%1,%2,%3}, [%4];" : "=r"(v.x), "=r"(v.y), "=r"(v.z), "=r"(v.w) : "l"(p) : "memory"); return v;
}
__device__ __forceinline__ void st_relaxed(uint32_t* p, uint32_t v) {
  asm volatile("st.relaxed.gpu.global.u32 [%0], %1;" ::"l"(p), "r"(v) : "memory");
}
__device__ __forceinline__ void st_relaxed4(uint32_t* p, uint32_t a, uint32_t b, uint32_t c, uint32_t d) {
  asm volatile("st.relaxed.gpu.global.v4.u32 [%0], {%1,%2,%3,%4};" ::"l"(p), "r"(a), "r"(b), "r"(c), "r"(d) : "memory");
}
__device__ __forceinline__ void st_b128(uint32_t* p, uint32_t a, uint32_t b, uint32_t c, uint32_t d) {
  asm volatile("{ .reg .b64 u, v; .reg .b128 w; mov.b64 u, {%1, %2}; mov.b64 v, {%3, %4}; mov.b128 w, {u, v}; st.relaxed.gpu.global.b128 [%0], w; }"
               ::"l"(p), "r"(a), "r"(b), "r"(c), "r"(d) : "memory");
}
__device__ __forceinline__ uint4 ld_b128(const uint32_t* p) {
  uint4 r;
  asm volatile("{ .reg .b64 u, v; .reg .b128 w; ld.relaxed.gpu.global.b128 w, [%4]; mov.b128 {u, v}, w; mov.b64 {%0, %1}, u; mov.b64 {%2, %3}, v; }"
               : "=r"(r.x), "=r"(r.y), "=r"(r.z), "=r"(r.w) : "l"(p) : "memory");
  return r;
}
__device__ __forceinline__ void st_pairs(uint32_t* p, uint32_t a, uint32_t b, uint32_t tag) {
  asm volatile("{ .reg .b64 u, v; mov.b64 u, {%1, %3}; mov.b64 v, {%2, %3}; st.relaxed.gpu.global.v2.b64 [%0], {u, v}; }"
               ::"l"(p), "r"(a), "r"(b), "r"(tag) : "memory");
}
__device__ __forceinline__ uint4 ld_pairs(const uint32_t* p) {
  uint4 v;
  asm volatile("{ .reg .b64 u, v; ld.relaxed.gpu.global.v2.b64 {u, v}, [%4]; mov.b64 {%0, %1}, u; mov.b64 {%2, %3}, v; }"
               : "=r"(v.x), "=r"(v.y), "=r"(v.z), "=r"(v.w) : "l"(p) : "memory");
  return v;
}
__device__ __forceinline__ uint2 ld_pair(const uint32_t* p) {
  uint2 v;
  asm volatile("{ .reg .b64 u; ld.relaxed.gpu.global.b64 u, [%2]; mov.b64 {%0, %1}, u; }" : "=r"(v.x), "=r"(v.y) : "l"(p) : "memory");
  return v;
}
__device__ __forceinline__ void red_release(uint32_t* p, uint32_t v) {
  asm volatile("red.release.gpu.global.add.u32 [%0], %1;" ::"l"(p), "r"(v) : "memory");
}
__device__ __forceinline__ uint32_t ldg_nc1(const void* p) {
  uint32_t v;
  asm volatile("ld.global.nc.u32 %0, [%1];" : "=r"(v) : "l"(p));
  return v;
}
__device__ __forceinline__ uint4 ldg_nc4(const void* p) {
  uint4 v; asm volatile("ld.global.nc.L1::no_allocate.v4.u32 {%0,%1,%2,%3}, [%4];" : "=r"(v.x), "=r"(v.y), "=r"(v.z), "=r"(v.w) : "l"(p)); return v;
}
__device__ __forceinline__ uint4 ldg_stream4(const void* p) {
  uint4 v;
  asm volatile("ld.global.nc.L1::no_allocate.L2::cache_hint.v4.u32 {%0,%1,%2,%3}, [%4], %5;" : "=r"(v.x), "=r"(v.y), "=r"(v.z), "=r"(v.w) : "l"(p), "l"(l2_stream()));
  return v;
}
__device__ __forceinline__ void stg4(void* p, uint4 v) {
  asm volatile("st.global.v4.u32 [%0], {%1,%2,%3,%4};" ::"l"(p), "r"(v.x), "r"(v.y), "r"(v.z), "r"(v.w) : "memory");
}
__device__ __forceinline__ void wait_counter(const uint32_t* p, uint32_t target) {
  uint32_t n = 0;
  while (__any_sync(0xffffffffu, (int)(ld_acquire(p) - target) < 0)) { watchdog(n); }
}
__device__ __forceinline__ uint32_t tagf(float v, uint32_t tag) { return (__float_as_uint(v) & ~3u) | tag; }
__device__ __forceinline__ bool tag_ok(uint4 v, uint32_t tag) { return (((v.x ^ tag) | (v.y ^ tag) | (v.z ^ tag) | (v.w ^ tag)) & 3u) == 0; }
__device__ __forceinline__ float untag_sum(uint32_t a, uint32_t b) { return __uint_as_float(a & ~3u) + __uint_as_float(b & ~3u); }
__device__ __forceinline__ uint4 poll4(const uint32_t* p, uint32_t tag) {
  uint4 v = ld_relaxed4(p);
  uint32_t n = 0;
  while (!__all_sync(0xffffffffu, tag_ok(v, tag))) { v = ld_relaxed4(p); watchdog(n); }
  return v;
}
__device__ __forceinline__ float bf_lo(uint32_t v) { return __uint_as_float(v << 16); }
__device__ __forceinline__ float bf_hi(uint32_t v) { return __uint_as_float(v & 0xffff0000u); }
__device__ __forceinline__ uint32_t pack_bf(float lo, float hi) {
  uint32_t r; asm("cvt.rn.bf16x2.f32 %0, %1, %2;" : "=r"(r) : "f"(hi), "f"(lo)); return r;
}
__device__ __forceinline__ float rbf(float v) { return __uint_as_float(pack_bf(0.f, v) & 0xffff0000u); }
__device__ __forceinline__ uint32_t hmul2(uint32_t a, uint32_t b) {
  uint32_t r; asm("mul.rn.bf16x2 %0, %1, %2;" : "=r"(r) : "r"(a), "r"(b)); return r;
}
__device__ __forceinline__ uint32_t hadd2(uint32_t a, uint32_t b) {
  uint32_t r; asm("add.rn.bf16x2 %0, %1, %2;" : "=r"(r) : "r"(a), "r"(b)); return r;
}
__device__ __forceinline__ uint32_t hsub2(uint32_t a, uint32_t b) {
  uint32_t r; asm("sub.rn.bf16x2 %0, %1, %2;" : "=r"(r) : "r"(a), "r"(b)); return r;
}
__device__ __forceinline__ float rcp(float x) { float r; asm("rcp.approx.ftz.f32 %0, %1;" : "=f"(r) : "f"(x)); return r; }
__device__ __forceinline__ float ex2(float x) { float r; asm("ex2.approx.ftz.f32 %0, %1;" : "=f"(r) : "f"(x)); return r; }
__device__ __forceinline__ void stmatrix4(uint32_t addr, uint32_t a, uint32_t b, uint32_t c, uint32_t d) {
  asm volatile("stmatrix.sync.aligned.m8n8.x4.shared.b16 [%0], {%1,%2,%3,%4};" ::"r"(addr), "r"(a), "r"(b), "r"(c), "r"(d) : "memory");
}
__device__ __forceinline__ void ldmatrix4(uint32_t addr, uint32_t& a, uint32_t& b, uint32_t& c, uint32_t& d) {
  asm volatile("ldmatrix.sync.aligned.m8n8.x4.shared.b16 {%0,%1,%2,%3}, [%4];" : "=r"(a), "=r"(b), "=r"(c), "=r"(d) : "r"(addr) : "memory");
}
__device__ __forceinline__ void ldmatrix4t(uint32_t addr, uint32_t& a, uint32_t& b, uint32_t& c, uint32_t& d) {
  asm volatile("ldmatrix.sync.aligned.m8n8.x4.trans.shared.b16 {%0,%1,%2,%3}, [%4];" : "=r"(a), "=r"(b), "=r"(c), "=r"(d) : "r"(addr) : "memory");
}
__device__ __forceinline__ void mma16816(float (&d)[4], uint32_t a0, uint32_t a1, uint32_t a2, uint32_t a3, uint32_t b0, uint32_t b1) {
  asm volatile("mma.sync.aligned.m16n8k16.row.col.f32.bf16.bf16.f32 {%0,%1,%2,%3}, {%4,%5,%6,%7}, {%8,%9}, {%0,%1,%2,%3};"
               : "+f"(d[0]), "+f"(d[1]), "+f"(d[2]), "+f"(d[3]) : "r"(a0), "r"(a1), "r"(a2), "r"(a3), "r"(b0), "r"(b1));
}
__device__ __forceinline__ void sts1(uint32_t a, uint32_t v) { asm volatile("st.shared.u32 [%0], %1;" ::"r"(a), "r"(v) : "memory"); }
__device__ __forceinline__ uint4 lds4(uint32_t a) {
  uint4 v; asm volatile("ld.shared.v4.u32 {%0,%1,%2,%3}, [%4];" : "=r"(v.x), "=r"(v.y), "=r"(v.z), "=r"(v.w) : "r"(a) : "memory"); return v;
}
__device__ __forceinline__ uint2 lds2(uint32_t a) {
  uint2 v; asm volatile("ld.shared.v2.u32 {%0,%1}, [%2];" : "=r"(v.x), "=r"(v.y) : "r"(a) : "memory"); return v;
}
__device__ __forceinline__ uint32_t lds1(uint32_t a) {
  uint32_t v; asm volatile("ld.shared.u32 %0, [%1];" : "=r"(v) : "r"(a) : "memory"); return v;
}
__device__ __forceinline__ void sts2(uint32_t a, uint32_t x, uint32_t y) { asm volatile("st.shared.v2.u32 [%0], {%1,%2};" ::"r"(a), "r"(x), "r"(y) : "memory"); }
__device__ __forceinline__ void sts4(uint32_t a, uint4 v) {
  asm volatile("st.shared.v4.u32 [%0], {%1,%2,%3,%4};" ::"r"(a), "r"(v.x), "r"(v.y), "r"(v.z), "r"(v.w) : "memory");
}
__device__ __forceinline__ float silu_f(float v) { return __fdividef(v, 1.f + __expf(-v)); }
__device__ __forceinline__ uint32_t hfma2(uint32_t a, uint32_t b, uint32_t c) {
  uint32_t r; asm("fma.rn.bf16x2 %0, %1, %2, %3;" : "=r"(r) : "r"(a), "r"(b), "r"(c)); return r;
}
__device__ __forceinline__ void split_inv(float sd, uint32_t& ih, uint32_t& il) {
  const float inv = rcp(sd);
  ih = pack_bf(inv, inv);
  const float lo = inv - bf_lo(ih);
  il = pack_bf(lo, lo);
}
__device__ __forceinline__ uint32_t ln_norm(uint32_t x, uint32_t mean2, uint32_t ih, uint32_t il) {
  const uint32_t d = hsub2(x, mean2);
  return hfma2(d, ih, hmul2(d, il));
}
__device__ __forceinline__ uint32_t ln_mod(uint32_t x, uint32_t mean2, uint32_t ih, uint32_t il, uint32_t c1, uint32_t sh) {
  return hadd2(hmul2(ln_norm(x, mean2, ih, il), c1), sh);
}

#define R8(a, i) "+f"(a[i]), "+f"(a[i + 1]), "+f"(a[i + 2]), "+f"(a[i + 3]), "+f"(a[i + 4]), "+f"(a[i + 5]), "+f"(a[i + 6]), "+f"(a[i + 7])
#define D64 "{%0,%1,%2,%3,%4,%5,%6,%7,%8,%9,%10,%11,%12,%13,%14,%15,%16,%17,%18,%19,%20,%21,%22,%23,%24,%25,%26,%27,%28,%29,%30,%31," \
            "%32,%33,%34,%35,%36,%37,%38,%39,%40,%41,%42,%43,%44,%45,%46,%47,%48,%49,%50,%51,%52,%53,%54,%55,%56,%57,%58,%59,%60,%61,%62,%63}"
template <int TB>
__device__ __forceinline__ void mma_ss(float (&d)[64], uint64_t da, uint64_t db, int sc) {
  asm volatile("{\n.reg .pred p;\nsetp.ne.b32 p, %66, 0;\n"
               "wgmma.mma_async.sync.aligned.m64n128k16.f32.bf16.bf16 " D64 ", %64, %65, p, 1, 1, 0, %67;\n}"
               : R8(d, 0), R8(d, 8), R8(d, 16), R8(d, 24), R8(d, 32), R8(d, 40), R8(d, 48), R8(d, 56)
               : "l"(da), "l"(db), "r"(sc), "n"(TB));
}
template <int TB>
__device__ __forceinline__ void mma_rs(float (&d)[64], uint32_t a0, uint32_t a1, uint32_t a2, uint32_t a3, uint64_t db, int sc) {
  asm volatile("{\n.reg .pred p;\nsetp.ne.b32 p, %69, 0;\n"
               "wgmma.mma_async.sync.aligned.m64n128k16.f32.bf16.bf16 " D64 ", {%64,%65,%66,%67}, %68, p, 1, 1, %70;\n}"
               : R8(d, 0), R8(d, 8), R8(d, 16), R8(d, 24), R8(d, 32), R8(d, 40), R8(d, 48), R8(d, 56)
               : "r"(a0), "r"(a1), "r"(a2), "r"(a3), "l"(db), "r"(sc), "n"(TB));
}
#define D128 "{%0,%1,%2,%3,%4,%5,%6,%7,%8,%9,%10,%11,%12,%13,%14,%15,%16,%17,%18,%19,%20,%21,%22,%23,%24,%25,%26,%27,%28,%29,%30,%31," \
             "%32,%33,%34,%35,%36,%37,%38,%39,%40,%41,%42,%43,%44,%45,%46,%47,%48,%49,%50,%51,%52,%53,%54,%55,%56,%57,%58,%59,%60,%61,%62,%63," \
             "%64,%65,%66,%67,%68,%69,%70,%71,%72,%73,%74,%75,%76,%77,%78,%79,%80,%81,%82,%83,%84,%85,%86,%87,%88,%89,%90,%91,%92,%93,%94,%95," \
             "%96,%97,%98,%99,%100,%101,%102,%103,%104,%105,%106,%107,%108,%109,%110,%111,%112,%113,%114,%115,%116,%117,%118,%119,%120,%121,%122,%123,%124,%125,%126,%127}"
#define R128(d, e) R8(d, 0), R8(d, 8), R8(d, 16), R8(d, 24), R8(d, 32), R8(d, 40), R8(d, 48), R8(d, 56), \
                   R8(e, 0), R8(e, 8), R8(e, 16), R8(e, 24), R8(e, 32), R8(e, 40), R8(e, 48), R8(e, 56)
__device__ __forceinline__ void mma256_ss(float (&d)[64], float (&e)[64], uint64_t da, uint64_t db, int sc) {
  asm volatile("{\n.reg .pred p;\nsetp.ne.b32 p, %130, 0;\n"
               "wgmma.mma_async.sync.aligned.m64n256k16.f32.bf16.bf16 " D128 ", %128, %129, p, 1, 1, 0, 1;\n}"
               : R128(d, e) : "l"(da), "l"(db), "r"(sc));
}
__device__ __forceinline__ void mma256_rs(float (&d)[64], float (&e)[64], uint32_t a0, uint32_t a1, uint32_t a2, uint32_t a3, uint64_t db) {
  asm volatile("{\n.reg .pred p;\nsetp.ne.b32 p, 1, 0;\n"
               "wgmma.mma_async.sync.aligned.m64n256k16.f32.bf16.bf16 " D128 ", {%128,%129,%130,%131}, %132, p, 1, 1, 1;\n}"
               : R128(d, e) : "r"(a0), "r"(a1), "r"(a2), "r"(a3), "l"(db));
}
template <int N> __device__ __forceinline__ void keep(float (&a)[N]) {
#pragma unroll
  for (int i = 0; i < N; i++) asm volatile("" : "+f"(a[i])::"memory");
}
template <int N> __device__ __forceinline__ void keep(uint32_t (&a)[N]) {
#pragma unroll
  for (int i = 0; i < N; i++) asm volatile("" : "+r"(a[i])::"memory");
}

#define STAMP(idx) do {} while (0)
#define PROF(grp, cond, idx) do {} while (0)

constexpr float SCL2 = 1.4426950408889634f * 0.08838834764831845f;

__device__ __forceinline__ void pack_p(const float (&s)[64], uint32_t (&p)[32]) {
#pragma unroll
  for (int i = 0; i < 32; i++) p[i] = pack_bf(s[2 * i], s[2 * i + 1]);
}

__device__ __forceinline__ void issue_qk(float (&s)[64], uint32_t q0, uint32_t q1, uint32_t kslot) {
  const uint64_t db = make_desc(kslot, 16, 1024), da0 = make_desc(q0, 16, 1024), da1 = make_desc(q1, 16, 1024);
#pragma unroll
  for (int kk = 0; kk < 8; kk++) mma_ss<0>(s, (kk < 4 ? da0 : da1) + (kk & 3) * 2, db + (kk >> 2) * 1024 + (kk & 3) * 2, kk != 0);
}
__device__ __forceinline__ void issue_pv(float (&o)[64], uint32_t (&p)[32], uint32_t vslot, int acc) {
  uint64_t db = make_desc(vslot, 16384, 1024);
#pragma unroll
  for (int kk = 0; kk < 8; kk++)
    mma_rs<1>(o, p[4 * kk], p[4 * kk + 1], p[4 * kk + 2], p[4 * kk + 3], db + kk * 128, kk == 0 ? acc : 1);
}

template <int H>
__device__ __forceinline__ void store_chunk(const float (&a)[64], uint32_t addr) {
#pragma unroll
  for (int i = 8 * H; i < 8 * H + 8; i += 2)
    stmatrix4(addr ^ ((i & 7) << 4), pack_bf(a[4 * i], a[4 * i + 1]), pack_bf(a[4 * i + 2], a[4 * i + 3]),
              pack_bf(a[4 * i + 4], a[4 * i + 5]), pack_bf(a[4 * i + 6], a[4 * i + 7]));
}
template <int H>
__device__ __forceinline__ void store_chunk(const float (&a)[64], float i0, float i1, uint32_t addr) {
#pragma unroll
  for (int i = 8 * H; i < 8 * H + 8; i += 2)
    stmatrix4(addr ^ ((i & 7) << 4), pack_bf(a[4 * i] * i0, a[4 * i + 1] * i0), pack_bf(a[4 * i + 2] * i1, a[4 * i + 3] * i1),
              pack_bf(a[4 * i + 4] * i0, a[4 * i + 5] * i0), pack_bf(a[4 * i + 6] * i1, a[4 * i + 7] * i1));
}
__device__ __forceinline__ float inv_quad_sum(float l) {
  l += __shfl_xor_sync(0xffffffffu, l, 1);
  l += __shfl_xor_sync(0xffffffffu, l, 2);
  return rcp(l);
}

__device__ __forceinline__ void write_table(uint32_t table, bool ca, uint32_t t, const uint4& m0, const uint4& m1) {
  float c0 = untag_sum(m0.x, m1.x), c1 = untag_sum(m0.y, m1.y), c2 = untag_sum(m0.z, m1.z), c3 = untag_sum(m0.w, m1.w);
  if (ca) { c0 = 1.f + rbf(c0); c1 = 1.f + rbf(c1); c2 = 1.f + rbf(c2); c3 = 1.f + rbf(c3); }
  const uint32_t d = table + (t >> 2) * 64 + (t & 1) * 32 + (t & 2) * 2 + (ca ? 0 : 8);
  sts1(d, pack_bf(c0, c1));
  sts1(d + 16, pack_bf(c2, c3));
}

__device__ __forceinline__ void ln_scalars(float mean, float var, float& mb, float& sd) {
  mb = rbf(mean);
  float r; asm("sqrt.approx.ftz.f32 %0, %1;" : "=f"(r) : "f"(rbf(rbf(var) + 1e-5f)));
  sd = rbf(r);
}

__global__ void __cluster_dims__(2, 1, 1) __launch_bounds__(384, 1) fused_kernel(const __grid_constant__ Maps maps, const Ptrs P) {
  extern __shared__ __align__(1024) uint8_t smem_raw[];
  const uint32_t base = smem_u32(smem_raw);
  const int tid = threadIdx.x, lane = tid & 31;
  const int warp = __shfl_sync(0xffffffffu, tid >> 5, 0);
  const int b = blockIdx.x;
  PROF(31, tid == 0, 0);

  if (b >= NMAIN) {
    float* sc = reinterpret_cast<float*>(smem_raw);
    float* red = sc + DM;
    for (int k = tid; k < DM; k += 384) sc[k] = rbf(silu_f(__bfloat162float(P.c[k])));
    __syncthreads();
    if (tid < 256) {
      const int col = 2048 + (b - NMAIN) * 1024 + (tid & 127) * 8, r0 = (tid >> 7) * 512;
      float acc[8];
#pragma unroll
      for (int e = 0; e < 8; e++) acc[e] = 0.f;
#pragma unroll 1
      for (int r = r0; r < r0 + 512; r += HU) {
        uint4 w[HU];
#pragma unroll
        for (int u = 0; u < HU; u++) w[u] = ldg_stream4(P.w_mod + (size_t)(r + u) * NMOD + col);
#pragma unroll
        for (int u = 0; u < HU; u++) {
          float s = sc[r + u];
          acc[0] += s * bf_lo(w[u].x); acc[1] += s * bf_hi(w[u].x); acc[2] += s * bf_lo(w[u].y); acc[3] += s * bf_hi(w[u].y);
          acc[4] += s * bf_lo(w[u].z); acc[5] += s * bf_hi(w[u].z); acc[6] += s * bf_lo(w[u].w); acc[7] += s * bf_hi(w[u].w);
        }
      }
      if (tid >= 128) {
#pragma unroll
        for (int e = 0; e < 8; e++) red[(tid & 127) * 8 + e] = acc[e];
      }
      const uint32_t tag = ld_relaxed(&g_epoch) % 3 + 1;
      bar_sync(1, 256);
      if (tid < 128) {
        uint32_t o[8];
#pragma unroll
        for (int e = 0; e < 8; e++) o[e] = __float_as_uint(rbf(acc[e] + red[tid * 8 + e])) | tag;
        st_relaxed4(g_mod + col, o[0], o[1], o[2], o[3]);
        st_relaxed4(g_mod + col + 4, o[4], o[5], o[6], o[7]);
        const uint4 wr = ldg_nc4(P.w_r + tid * 8);
        const uint32_t wv[4] = {wr.x, wr.y, wr.z, wr.w};
        float dsum = 0.f;
#pragma unroll
        for (int e = 0; e < 8; e++) {
          const float m = bf_hi(o[e]);
          dsum += (b == NMAIN + 2 ? rbf(1.f + m) : m) * ((e & 1) ? bf_hi(wv[e >> 1]) : bf_lo(wv[e >> 1]));
        }
#pragma unroll
        for (int k = 16; k > 0; k >>= 1) dsum += __shfl_xor_sync(0xffffffffu, dsum, k);
        if (lane == 0) st_relaxed(g_mod + (b - NMAIN) * 4 + warp, tagf(dsum, tag));
      }
    }
    PROF(2, tid == 0, 1);
    return;
  }

  const int rank = b & 1;
  const int rb = ((b >> 4) << 1) | rank, cj = (b >> 1) & 7;
  const bool late = b & 4;
  const uint32_t bfull = base + OFF_BAR, bempty = bfull + NSLOT * 8;
  const uint32_t gfull = bempty + NSLOT * 8, gempty = gfull + 32;
  const uint32_t bar_ofull = gempty + 32;
  const uint32_t bar_ofree = bar_ofull + 32;
  const uint32_t bar_par = bar_ofree + 32;
  const uint32_t bar_mod = bar_par + 8;
  const uint32_t bar_pread = bar_mod + 8;
  const uint32_t bar_xres = bar_pread + 8;
  const uint32_t bar_ring = bar_xres + 8;
  const uint32_t bar_box = bar_ring + 24;
  const uint32_t bar_go = bar_box + 96;
  const uint32_t bar_go2 = bar_go + 16;
  const uint32_t bar_cnt = bar_go + 24;
  const uint32_t xfull = bar_go + 40, xempty = xfull + 32;
  const uint32_t bar_hw = xempty + 32, bar_hx = bar_hw + 8;
  const uint32_t bar_hpub = bar_hx + 16;
  const uint32_t bar_win = bar_hpub + 16;
  const uint32_t bar_rx = bar_win + 8;
  const uint32_t bar_sel = bar_rx + 8;
  const uint32_t bar_gate = bar_sel + 8;
  const uint32_t bar_rel = bar_gate + 8;
  const uint32_t bar_od = bar_rel + 8;
  const uint32_t bar_mod2 = bar_od + 8;
  const uint32_t bar_res = bar_go + 8;
  const uint32_t stage = base + OFF_STAGE, par = base + OFF_PAR;

  if (warp == 10 && elect_one()) prefetch_map(&maps.wm);
  if (warp == 8 && elect_one()) {
    for (int s = 0; s < NSLOT; s++) { mbar_init(bfull + s * 8, 1); mbar_init(bempty + s * 8, 16); }
    for (int s = 0; s < 4; s++) { mbar_init(gfull + s * 8, 1); mbar_init(gempty + s * 8, 16); mbar_init(xfull + s * 8, 1); mbar_init(xempty + s * 8, 8); mbar_init(bar_ofree + s * 8, 1); mbar_init(bar_ofull + s * 8, 128); }
    mbar_init(bar_par, 64); mbar_init(bar_mod, 256); mbar_init(bar_pread, 2); mbar_init(bar_xres, 1);
    mbar_init(bar_ring, 8); mbar_init(bar_ring + 8, 8); mbar_init(bar_ring + 16, 8);
    mbar_init(bar_go, 1); mbar_init(bar_go2, 1); mbar_init(bar_cnt, 1); mbar_init(bar_cnt + 8, 1); mbar_init(bar_hpub, 8); mbar_init(bar_hpub + 8, 8); mbar_init(bar_res, 1); mbar_init(bar_win, 1); mbar_init(bar_rx, 1); mbar_init(bar_sel, 64); mbar_init(bar_gate, 8); mbar_init(bar_rel, 8); mbar_init(bar_od, 1); mbar_init(bar_mod2, 64);
    for (int s = 0; s < 12; s++) mbar_init(bar_box + s * 8, 1);
    asm volatile("fence.mbarrier_init.release.cluster;" ::: "memory");
    prefetch_map(&maps.x); prefetch_map(&maps.wq); prefetch_map(&maps.k); prefetch_map(&maps.v);
  }
  if (warp == 9 && elect_one()) {
    mbar_init(bar_hw, 1); mbar_init(bar_hx, 1); mbar_init(bar_hx + 8, 1);
    asm volatile("fence.mbarrier_init.release.cluster;" ::: "memory");
    mbar_expect_tx(bar_hw, 32768);
    mbar_expect_tx(bar_hx, 16384);
    mbar_expect_tx(bar_hx + 8, 16384);
    const __nv_bfloat16* xs = P.x + (size_t)(rb * 128 + cj * 16) * DM;
    bulk_load(base + 2 * GST_BYTES, xs, 16384, bar_hx);
    if (!late) {
      tma2d(stage, &maps.wm, (b >> 1) * 32, rank * 512, bar_hw);
      tma2d(stage + 16384, &maps.wm, (b >> 1) * 32, rank * 512 + 256, bar_hw);
    }
    bulk_load(base + 3 * GST_BYTES, xs + 8 * DM, 16384, bar_hx + 8);
  }
  cluster_arrive();

  if (warp >= 8) {
    asm volatile("setmaxnreg.dec.sync.aligned.u32 40;");
    if (warp < 10) bar_arrive(1, 320);
    const uint32_t epoch = ld_relaxed(&g_epoch);
    cluster_wait();
    if (warp == 8) {
      const int kvrow = (cj >> 1) * SK + (SK - WIN);
      int wch = cj * 8 + rank * 2;
#pragma unroll 1
      for (int ps = 0; ps < 3; ps++) {
        const CUtensorMap* mw = ps == 2 ? &maps.wo : &maps.wq;
        const uint32_t xt = ps == 1 ? XT1 : XT2, wt = ps == 0 ? WT0 : (ps == 1 ? WT1 : WT2);
        const int nst = ps == 2 ? 32 : 16;
#pragma unroll 1
        for (int i = 0; i < nst; i++) {
          const uint32_t bf = gfull + (i & 3) * 8;
          const int kt = ps == 2 ? (((cj & 1) * 4 + ((i >> 1) & 3)) * 4 + (i >> 3)) * 2 + (i & 1) : (ps ? i : slice_of(i) + (b & 14)) & 15;
          const uint32_t wd = base + unit_of(wt, i & 3) + rank * UNIT, xd = base + unit_of(xt, i & 3);
          const uint8_t* xs = g_act + (uint32_t)(rb * 80 + (ps - 1) * 16 + kt) * UNIT;
          if (ps == 0 && i == HD) mbar_wait(bar_mod, 0);
          if (ps == 2 && (i & 7) == 0 && i != 8) mbar_wait(i ? bar_cnt + i - 16 : bar_ofree + 24, 0);
          if ((i & 7) == 0) fence_async();
          if (i == RES0) mbar_wait(bar_res, 0);
          mbar_wait(bf, ((i >> 2) & 1) ^ 1);
          if (elect_one()) {
            mbar_expect_tx(bf, ps ? GST_BYTES : 2 * UNIT);
            if (ps && i < 2) bulk_load_stream(xd, xs, UNIT, bf);
            mbar_arrive_pred(bar_go, i == GOST);
            mbar_arrive_pred(bar_go2, ps == 1 && i == PG0);
            mbar_arrive_pred(bar_od, ps && i == (ps == 1 ? ODS1 : ODS) + 1);
            if (i == RES0) mbar_expect_tx(bar_xres, 32768);
          }
          const int wk = (i == 31 ? kt ^ (rank * 32) : kt) * 64, wc = i == 31 ? cj * 2 : wch;
          const uint64_t xp = i == 31 ? l2_normal() : l2_stream();
          mbar_wait(ps && i < 4 ? bempty + i * 8 : gempty + (i & 3) * 8, ((i >> 2) & 1) ^ 1);
          if (elect_one()) {
            tma3d_mc<true>(wd, mw, 0, wk, wc, bf);
            if (ps && i > 2) bulk_load_stream(xd, xs, UNIT, bf, xp);
            if (i == RES0 || i == RES1) tma2d(base + OFF_RES + (i == RES1) * UNIT, &maps.x, cj * 128 + (i == RES1) * 64, rb * 128, bar_xres);
          }
          if (ps && i == 2) {
            mbar_wait(bar_ofree + (ps - 1) * 16, 0);
            if (elect_one()) bulk_load_stream(xd, xs, UNIT, bf);
          }
        }
        if (ps == 2) break;
        wch = ps ? ((wch >> 3) ^ rank) * 2 : wch + 4;
#pragma unroll 1
        for (int u = 0; u < 16; u++) {
          const bool isk = (u == 0) || ((u & 1) && u < 15);
          const int blk = (isk ? (u + 1) >> 1 : (u == 15 ? 7 : (u >> 1) - 1)) & 3;
          const uint32_t sl = base + unit_of(ps ? AT1 : AT0, u & 3) + rank * UNIT, bf = bfull + (u & 3) * 8;
          mbar_wait(bf, ((u >> 2) & 1) ^ 1);
          if (elect_one()) mbar_expect_tx(bf, SLOT_BYTES);
          mbar_wait(u < 4 ? gempty + ((u + 1) >> 1) * 8 : bempty + (u & 3) * 8, ((u >> 2) & 1) ^ 1);
          if (elect_one()) {
            if (ps && u >= 7 && u != 8) tma3d_mc<true>(sl, isk ? &maps.k : &maps.v, 0, kvrow + blk * 128, rank, bf);
            else tma3d_mc<false>(sl, isk ? &maps.k : &maps.v, 0, kvrow + blk * 128, rank, bf);
          }
        }
      }
      if (elect_one()) mbar_expect_tx(bar_rx, UNIT);
      mbar_wait(bar_rel, 0);
      if (elect_one()) {
        bulk_load_stream(base + UNIT, g_act + (uint32_t)(rb * 80 + 16 + 63 - (cj & 1) * 32) * UNIT, UNIT, bar_rx);
      }
      if (b < NFFN) {
#pragma unroll 1
        for (int u = 0; u < 12; u++) {
          const uint32_t dst = base + unit_of(u < 4 ? FT_G : (u < 8 ? FT_U : FT_D), u & 3);
          if (elect_one()) mbar_expect_tx(bar_box + u * 8, UNIT);
          if (u == 0 || u == 2 || u == 8) mbar_wait(bar_ring + (u == 8 ? 16 : u * 4), 0);
          const int fp = u < 8 ? FPACE0 : FPACE;
          if (u >= fp) mbar_wait(bar_box + (u - fp) * 8, 0);
          if (elect_one()) {
            if (u < 8) tma2d(dst, u < 4 ? &maps.wg : &maps.wu, b * 32, (u & 3) * 256, bar_box + u * 8);
            else tma3d(dst, &maps.wd, 0, b * 32, (u - 8) * 4, bar_box + u * 8);
          }
        }
      }
    } else if (warp == 9) {
      const uint32_t target = 8 * (epoch + 1);
      uint32_t hmask = 0;
#pragma unroll 1
      for (int i = 0; i < 16; i++) {
        if (i == HDX) mbar_wait(bar_mod, 0);
        const int kt = (2 * cj + slice_of(i)) & 15;
        const uint32_t need = i == 15 ? 0xffffu : 1u << kt;
        if (i >= NRS && (hmask & need) != need) {
          uint32_t n = 0;
          do { hmask = __ballot_sync(0xffffffffu, ld_acquire(&g_cnt_h[rb * 32 + (lane & 15)]) == epoch + 1); watchdog(n); } while ((hmask & need) != need);
          PROF(1, lane == 0 && i == NRS, 26);
          fence_async();
        }
        mbar_wait(xempty + (i & 3) * 8, ((i >> 2) & 1) ^ 1);
        if (elect_one()) {
          mbar_expect_tx(xfull + (i & 3) * 8, UNIT);
          if (i < NRS) tma2d(base + (i & 3) * GST_BYTES, &maps.x, kt * 64, rb * 128, xfull + (i & 3) * 8);
          else bulk_load_stream(base + (i & 3) * GST_BYTES, g_act + (uint32_t)(rb * 80 + kt) * UNIT, UNIT, xfull + (i & 3) * 8);
        }
      }
      prefetch_map(&maps.wo);
#pragma unroll 1
      for (int t = 0; t < 4; t++) {
        if (t & 1) mbar_wait(bar_od, t >> 1);
        const int ops = OPS >> (t & 1);
#pragma unroll 1
        for (int p = 0; p < 32768; p += ops) {
          const uint32_t w = p >> 14, c = (p >> 13) & 1, off = w * 8192 + (p & 8191);
          mbar_wait(bar_ofull + (t & 1) * 16 + w * 8, t >> 1);
          if (elect_one()) {
            bulk_store(g_act + (uint32_t)(rb * 80 + 16 + (cj * 4 + t) * 2 + c) * UNIT + off, base + unit_of(QT, 2 * t + c) + off, ops);
            asm volatile("cp.async.bulk.commit_group;" ::: "memory");
            asm volatile("cp.async.bulk.wait_group.read 0;" ::: "memory");
          }
        }
        if (elect_one()) {
          mbar_arrive(t < 3 ? bar_ofree + t * 8 : bar_res);
          asm volatile("cp.async.bulk.wait_group 0;" ::: "memory");
          fence_async();
          red_release(&g_cnt_o[((rb * 4 + t) * 2 + (cj >> 2)) * 32], 2);
        }
        if (t) {
          wait_counter(&g_cnt_o[(rb * 8 + 2 * t + (cj & 1)) * 32], target);
          if (t & 1) wait_counter(&g_cnt_o[(rb * 8 + (t == 1 ? cj & 1 : 7 - (cj & 1))) * 32], target);
          if (elect_one()) mbar_arrive(t == 1 ? bar_ofree + 24 : bar_cnt + t * 8 - 16);
        }
      }
      PROF(2, lane == 0, 27);
      const uint32_t tag = epoch % 3 + 1;
      const uint32_t* inbox = g_cand + (b >> 1) % CR * 512 + (lane & 15) * CS;
      mbar_wait(bar_ring + 16, 0);
      uint32_t c0 = ld_relaxed(inbox), n = 0;
#define CAND_STEP(cv)                                                                                        \
      {                                                                                                      \
        const bool valid = (cv & 3u) == tag, all = __all_sync(0xffffffffu, valid);                           \
        const uint32_t best = __reduce_max_sync(0xffffffffu, valid ? cv : 0u);                               \
        const uint32_t blk = __ffs(__ballot_sync(0xffffffffu, cv == best)) - 1;                              \
        if (best) sts2(par + PAR_CONST + 56, best, (blk << 7 | (~best >> 2 & 127)) | (all ? 0x1800 : 0x800)); \
        if (all) break;                                                                                      \
        cv = ld_relaxed(inbox);                                                                              \
      }
      while (true) { CAND_STEP(c0) watchdog(n); }
    } else {
      const int t2 = tid - 320;
      if (late && warp == 10) {
        mbar_wait(bar_hx, 0);
        if (elect_one()) {
          tma2d(stage, &maps.wm, (b >> 1) * 32, rank * 512, bar_hw);
          tma2d(stage + 16384, &maps.wm, (b >> 1) * 32, rank * 512 + 256, bar_hw);
        }
      }
      {
        const uint32_t tag = epoch % 3 + 1;
        mbar_wait(bar_hx + 8, 0);
        mbar_wait(bar_hw, 0);
        __nanosleep(late ? OSL2 : OSL);
        {
          const uint32_t t7 = (warp & 1) * 64 + (lane >> 4) * 32 + 16 + (lane & 15);
          const uint32_t* pm = g_modp + ((cj * 128 + t7 * 4) & (DM - 1));
          uint4 m0, m1, m2, m3;
          uint32_t n = 0;
          do {
            m0 = ld_relaxed4(pm); m1 = ld_relaxed4(pm + 2 * DM); m2 = ld_relaxed4(pm + DM); m3 = ld_relaxed4(pm + 3 * DM);
            watchdog(n);
          } while (!__all_sync(0xffffffffu, tag_ok(m0, tag) && tag_ok(m1, tag) && tag_ok(m2, tag) && tag_ok(m3, tag)));
          write_table(par, false, t7, m0, m1);
          write_table(par, true, t7, m2, m3);
          mbar_arrive(bar_mod2);
        }
      }
      mbar_wait(bar_hpub + (warp & 1) * 8, 0);
      PROF(1, t2 == 0, 24);
#pragma unroll 1
      for (int c = 0; c < 8; c++) {
        const uint32_t off = (warp & 1) * UNIT + c * 2048 + lane * 16;
        uint8_t* dst = g_act + (uint32_t)(rb * 80 + cj * 2) * UNIT + off;
        const uint4 v0 = lds4(stage + off), v1 = lds4(stage + off + 512), v2 = lds4(stage + off + 1024), v3 = lds4(stage + off + 1536);
        stg4(dst, v0); stg4(dst + 512, v1); stg4(dst + 1024, v2); stg4(dst + 1536, v3);
      }
      __syncwarp();
      PROF(1, t2 == 0, 15);
      if (lane == 0) {
        mbar_arrive(bar_pread);
        red_release(&g_cnt_h[rb * 32 + cj * 2 + (warp & 1)], 1);
        PROF(1, t2 == 0, 25);
        prefetch_map(&maps.wg); prefetch_map(&maps.wu); prefetch_map(&maps.wd); prefetch_map(&maps.out);
      }
      __syncwarp();
      if (b < NFFN) {
        mbar_wait(bar_go2, 0);
        const __nv_bfloat16* pg = ((b & 1) ? P.w_up : P.w_gate) + (b >> 1) * 64 + (size_t)t2 * FF;
        const __nv_bfloat16* pd = P.w_down + (size_t)b * 32768 + t2 * 64;
        PROF(2, t2 == 0, 13);
#pragma unroll 1
        for (int i = 0; i < WN; i += WB) {
          uint32_t v[WB];
#pragma unroll
          for (int u = 0; u < WB; u++) {
            const int k = i + u;
            asm volatile("ld.global.cg.L2::128B.u32 %0, [%1];" : "=r"(v[u]) : "l"(k < 16 ? pg + (size_t)k * 64 * FF : pd + (k - 16) * 4096));
          }
#pragma unroll
          for (int u = 1; u < WB; u++) v[0] ^= v[u];
          sts1(par + PAR_SINK + t2 * 4, v[0]);
        }
        PROF(2, t2 == 0, 14);
      }
      const uint32_t tag = epoch % 3 + 1;
      mbar_wait(bar_go, 0);
      bar_sync(4, 64);
      if (warp == 10) {
        const uint32_t* src = g_mod + 2 * DM + cj * 128 + lane * 4;
        const uint2 wr = *reinterpret_cast<const uint2*>(P.w_r + cj * 128 + lane * 4);
        uint4 vga, vsb, vcb, vgb;
        uint32_t n = 0;
        do {
          vga = ld_relaxed4(src); vsb = ld_relaxed4(src + DM); vcb = ld_relaxed4(src + 2 * DM); vgb = ld_relaxed4(src + 3 * DM);
          watchdog(n);
        } while (!__all_sync(0xffffffffu, tag_ok(vga, tag) && tag_ok(vsb, tag) && tag_ok(vcb, tag) && tag_ok(vgb, tag)));
        const float c0 = rbf(1.f + bf_hi(vcb.x)), c1 = rbf(1.f + bf_hi(vcb.y)), c2 = rbf(1.f + bf_hi(vcb.z)), c3 = rbf(1.f + bf_hi(vcb.w));
        const float a0 = c0 * bf_lo(wr.x), a1 = c1 * bf_hi(wr.x), a2 = c2 * bf_lo(wr.y), a3 = c3 * bf_hi(wr.y);
        const uint32_t h0 = pack_bf(a0, a1), h1 = pack_bf(a2, a3);
        const uint32_t t1 = par + PAR_T1 + (lane >> 2) * 64 + (lane & 1) * 32 + (lane & 2) * 2;
        sts1(t1, h0); sts1(t1 + 8, pack_bf(a0 - bf_lo(h0), a1 - bf_hi(h0)));
        sts1(t1 + 16, h1); sts1(t1 + 24, pack_bf(a2 - bf_lo(h1), a3 - bf_hi(h1)));
        const uint32_t tg = par + PAR_SINK + (lane >> 3) * 64 + (lane & 1) * 32 + (lane & 6) * 2;
        sts1(tg, __byte_perm(vga.x, vga.y, 0x7632)); sts1(tg + 16, __byte_perm(vga.z, vga.w, 0x7632));
        sts4(par + PAR_T2 + lane * 32, make_uint4(pack_bf(c0, c1), __byte_perm(vsb.x, vsb.y, 0x7632), __byte_perm(vgb.x, vgb.y, 0x7632), __byte_perm(vga.x, vga.y, 0x7632)));
        sts4(par + PAR_T2 + lane * 32 + 16, make_uint4(pack_bf(c2, c3), __byte_perm(vsb.z, vsb.w, 0x7632), __byte_perm(vgb.z, vgb.w, 0x7632), __byte_perm(vga.z, vga.w, 0x7632)));
      } else {
        const uint4 g = poll4((lane & 8) ? g_mod + 8 - (lane & 1) * 4 : g_mod + 5 * DM + (b >> 4) * 128 + (lane & 7) * 16 + (b & 12), tag);
        sts1(par + PAR_CONST + 60, 0);
        sts1(par + PAR_CONST + 48, 0);
        if (lane < 8) sts1(par + PAR_CONST + 16 + lane * 4, (b & 2) ? ((b & 1) ? g.w : g.z) : ((b & 1) ? g.y : g.x));
        else if (lane < 10) sts2(par + PAR_CONST + (lane - 8) * 8, __float_as_uint(untag_sum(g.x, g.y) + untag_sum(g.z, g.w)), epoch);
      }
      __syncwarp();
#pragma unroll 1
      for (int q = 0; q < 32; q++) {
        st_b128(g_xch + ((size_t)b * 8 * 256 + q * 64 + t2) * 4, (epoch & 1) << 16, 0, 0, 0);
        __nanosleep(RSL);
      }
      for (int q = 0; q < 2; q++) st_relaxed4(g_stats + (((rb * 8 + q * 4 + (t2 >> 4)) * 8 + cj) * 16 + (t2 & 15)) * 4, 0, 0, 0, 0);
      if (b < NFFN)
        for (int q = 0; q < 2; q++) st_relaxed4(ypart_slot(b, q * 64 + t2), 0, 0, 0, 0);
      st_relaxed4(g_row + rb * 2 * DM + (t2 >> 5) * DM + cj * 128 + (t2 & 31) * 4, 0, 0, 0, 0);
      __threadfence();
      mbar_arrive(bar_par);
      mbar_wait(bar_gate, 0);
      uint32_t have = 0, n = 0;
      while (true) {
        const uint32_t st = lds1(par + PAR_CONST + 60) >> 7;
        if ((st & 31) != have) {
          const uint32_t* hsrc = g_row + (st & 15) * 2 * DM + t2 * 4;
          uint4 hv[4];
          bool ok = true;
#pragma unroll
          for (int i = 0; i < 4; i++) hv[i] = ld_pairs(hsrc + i * 256);
#pragma unroll
          for (int i = 0; i < 4; i++) {
            sts2(base + ((FT_G >> i * 4) & 15) * UNIT + (warp & 1) * 8192 + 256 + lane * 8, hv[i].x, hv[i].z);
            ok = ok && hv[i].y == tag && hv[i].w == tag;
          }
          have = __all_sync(0xffffffffu, ok) ? st & 31 : 0;
        }
        if ((st ^ have) == 32) break;
        watchdog(n);
      }
      mbar_arrive(bar_sel);
    }
    __syncwarp();
    cluster_arrive();
    {
      const uint32_t tag = epoch % 3 + 1, t3 = tid - 256;
      mbar_wait(bar_win, 0);
      uint2 win = lds2(par + PAR_CONST + 56);
      win.y &= 0x7ff;
      const uint32_t* fsrc = g_row + (win.y >> 7) * 2 * DM + (b >> 4) * 128 + (t3 & 7) * 16 + (b & 6) * 2 + ((b >> 2) & 2);
      const uint32_t* ysrc = ypart_slot(min(t3, NFFN - 1), b);
      uint2 fh = ld_pair(fsrc), fx = ld_pair(fsrc + DM);
      uint4 ya = ld_b128(ysrc);
      const float rwin = __uint_as_float(((int)win.x < 0 ? win.x & 0x7fffffffu : ~win.x) & ~0x1ffu);
      const float rs = rbf(rcp(1.f + __expf(-rbf(rwin))));
      uint32_t n = 0;
      while (__any_sync(0xffffffffu, fh.y != tag || fx.y != tag)) { fh = ld_pair(fsrc); fx = ld_pair(fsrc + DM); watchdog(n); }
      while (true) {
        const bool miss = ((ya.x & 1) | (ya.y & 1) << 1) != tag;
        if (!__any_sync(0xffffffffu, miss)) break;
        if (miss) ya = ld_b128(ysrc);
        watchdog(n);
      }
      PROF(8, t3 == 0, 5);
      float y[8] = {bf_lo(ya.x & ~1u), bf_hi(ya.x), bf_lo(ya.y & ~1u), bf_hi(ya.y), bf_lo(ya.z), bf_hi(ya.z), bf_lo(ya.w), bf_hi(ya.w)};
#pragma unroll
      for (int h = 4; h > 0; h >>= 1) {
        const bool up = lane & (h * 2);
#pragma unroll
        for (int e = 0; e < h; e++) y[e] = (up ? y[e + h] : y[e]) + __shfl_xor_sync(0xffffffffu, up ? y[e] : y[e + h], h * 2);
      }
      y[0] += __shfl_xor_sync(0xffffffffu, y[0], 1);
      if (!(lane & 1)) sts1(par + PAR_RED + 64 + t3 * 2, __float_as_uint(y[0]));
      bar_sync(4, 128);
      if (t3 < 8) {
        float y0 = 0.f;
#pragma unroll
        for (int w7 = 0; w7 < 7; w7++) y0 += __uint_as_float(lds1(par + PAR_RED + 64 + w7 * 32 + t3 * 4));
        const uint32_t gv = lds1(par + PAR_CONST + 16 + t3 * 4);
        const uint32_t upd = hmul2(pack_bf(y0, y0), pack_bf(rs, rs));
        const uint32_t r = hadd2(fx.x, hmul2(__byte_perm(gv, gv, 0x3232), hadd2(fh.x, upd)));
        reinterpret_cast<uint16_t*>(P.out)[(size_t)win.y * DM + (b >> 4) * 128 + t3 * 16 + (b & 15)] = (b & 1) ? r >> 16 : r;
        if (b == 0 && t3 == 0) st_relaxed(&g_epoch, epoch + 1);
      }
      PROF(31, t3 == 0, 36);
    }
    cluster_wait();
  } else {
    const int wg = warp >> 2;

    uint32_t tag;
    {
      uint32_t* const pmod = g_modp + rank * 2 * DM + (b >> 1) * 32 + lane;
      uint32_t* const pln = g_ln1 + (rb * 128 + cj * 16 + warp) * 4;
      uint32_t sc[8];
#pragma unroll
      for (int k = 0; k < 8; k++) sc[k] = ldg_nc1(P.c + rank * 512 + warp * 64 + k * 8 + (lane & 3) * 2);
      const uint32_t epoch = ld_relaxed(&g_epoch);
      if (warp == 0) st_relaxed(pmod, 0);
      if (lane == 0) { st_b128(pln, 0, 0, 0, 0); st_b128(pln + 32, 0, 0, 0, 0); }
      asm volatile("setmaxnreg.inc.sync.aligned.u32 232;");
      bar_sync(1, 320);
#pragma unroll
      for (int k = 0; k < 8; k++) sc[k] = pack_bf(silu_f(bf_lo(sc[k])), silu_f(bf_hi(sc[k])));
      keep(sc);
      tag = epoch % 3 + 1;
#pragma unroll
      for (int part = 0; part < 4; part++) {
        if (!(part & 1)) {
          const uint32_t xa = base + (2 + part / 2) * GST_BYTES + warp * 2048 + lane * 16;
          mbar_wait(bar_hx + part * 4, 0);
          float s0 = 0.f, s1 = 0.f, q0 = 0.f, q1 = 0.f;
#pragma unroll
          for (int q = 0; q < 4; q++) {
            const uint4 xv = lds4(xa + q * 512);
            const uint32_t u[4] = {xv.x, xv.y, xv.z, xv.w};
#pragma unroll
            for (int e = 0; e < 4; e++) { const float lo = bf_lo(u[e]), hi = bf_hi(u[e]); s0 += lo; s1 += hi; q0 += lo * lo; q1 += hi * hi; }
          }
          s0 += s1; q0 += q1;
#pragma unroll
          for (int o = 16; o > 0; o >>= 1) { s0 += __shfl_xor_sync(0xffffffffu, s0, o); q0 += __shfl_xor_sync(0xffffffffu, q0, o); }
          const float mean = s0 * (1.f / DM);
          float mb, sd;
          ln_scalars(mean, fmaxf(q0 * (1.f / DM) - mean * mean, 0.f), mb, sd);
          uint32_t ih, il;
          split_inv(sd, ih, il);
          if (lane == 0) st_b128(pln + part * 16, pack_bf(mb, mb), ih, il, tag);
          PROF(1, tid == 0 && part == 2, 4);
        } else if (late == (part == 3)) {
          const uint32_t fr = (lane & 7) + (lane >> 4) * 8, tq = lane & 3;
          const uint32_t wa = stage + warp * 4096 + fr * 64 + ((((lane >> 3) & 1) ^ ((fr >> 1) & 3)) << 4);
          float d0[4] = {0.f, 0.f, 0.f, 0.f}, d1[4] = {0.f, 0.f, 0.f, 0.f};
          mbar_wait(bar_hw, 0);
#pragma unroll
          for (int ks = 0; ks < 4; ks++) {
            uint32_t w[8];
            ldmatrix4t(wa + ks * 1024, w[0], w[1], w[2], w[3]);
            ldmatrix4t((wa ^ 32) + ks * 1024, w[4], w[5], w[6], w[7]);
            mma16816(d0, w[0], w[1], w[2], w[3], sc[2 * ks], sc[2 * ks + 1]);
            mma16816(d1, w[4], w[5], w[6], w[7], sc[2 * ks], sc[2 * ks + 1]);
          }
          sts1(base + 2 * GST_BYTES + warp * 2048 + (tq * 8 + (lane >> 2)) * 4, __float_as_uint((tq & 2) ? ((tq & 1) ? d1[2] : d1[0]) : ((tq & 1) ? d0[2] : d0[0])));
          bar_sync(1, 256);
          if (warp == 0) {
            float s = 0.f;
#pragma unroll
            for (int w8 = 0; w8 < 8; w8++) s += __uint_as_float(lds1(base + 2 * GST_BYTES + w8 * 2048 + lane * 4));
            st_relaxed(pmod, (__float_as_uint(s) & ~3u) | tag);
          }
          PROF(1, tid == 0, 3);
        }
      }
      cluster_wait();
      if (wg == 1) bar_arrive(2, 256);
    }

    float f0 = 0.f, f1 = 0.f;
    const uint32_t rempty = lane < 2 ? mapa(bempty, lane & 1) : 0;
    constexpr uint32_t GE = NSLOT * 8 + 32;
    float o[64], s[64];
#pragma unroll 1
    for (int ps = 0; ps < 3; ps++) {
      {
        const uint32_t xt = ps == 1 ? XT1 : XT2, wt = ps == 1 ? WT1 : WT2;
        const int nst = ps == 2 ? 28 : 14;
        if (ps == 0) {
          float ga[64], gb[64];
#pragma unroll
          for (int i = 0; i < 64; i++) { ga[i] = 0.f; gb[i] = 0.f; }
          uint32_t a[2][16];
          const uint32_t l = fresh_lane();
          uint32_t fa[4];
#pragma unroll
          for (int kk = 0; kk < 4; kk++) fa[kk] = (base + wg * 8192 + frag_offset(warp)) ^ (kk * 32);
          const uint32_t mt = par + (l & 3) * 16;
          auto fetch = [&](int i, uint32_t (&f)[16], uint32_t z) {
            mbar_wait(xfull + (i & 3) * 8, i >> 2);
#pragma unroll
            for (int kk = 0; kk < 4; kk++) ldmatrix4(fa[kk] + (i & 3) * GST_BYTES + z, f[4 * kk], f[4 * kk + 1], f[4 * kk + 2], f[4 * kk + 3]);
          };
          const bool oddw = warp & 2;
          uint4 r0, r1;
          {
            const uint32_t t7 = (warp & 1) * 64 + (l >> 4) * 32 + (l & 15);
            const uint32_t* pm = g_modp + wg * DM + ((cj * 128 + t7 * 4) & (DM - 1));
            const uint32_t* pr = g_ln1 + (rb * 128 + warp * 16 + (l >> 2)) * 4;
            uint4 m0 = make_uint4(tag, tag, tag, tag), m1 = m0;
            if (!oddw) { m0 = ld_relaxed4(pm); m1 = ld_relaxed4(pm + 2 * DM); }
            r0 = ld_b128(pr); r1 = ld_b128(pr + 32);
            fetch(0, a[0], 0); fetch(1, a[1], 0);
            uint32_t n = 0;
            bool written = false;
#pragma unroll 1
            while (true) {
              uint32_t miss;
              asm volatile("{ .reg .pred p0, p1, p2, p3; .reg .b32 t, u;\n"
                           "lop3.b32 t, %1, %2, %19, 0x7e; lop3.b32 u, %3, %4, %19, 0x7e; or.b32 t, t, u; and.b32 t, t, 3; setp.ne.u32 p0, t, 0;\n"
                           "lop3.b32 t, %5, %6, %19, 0x7e; lop3.b32 u, %7, %8, %19, 0x7e; or.b32 t, t, u; and.b32 t, t, 3; setp.ne.u32 p1, t, 0;\n"
                           "setp.ne.u32 p2, %12, %19; setp.ne.u32 p3, %16, %19;\n"
                           "@p0 ld.relaxed.gpu.global.v4.u32 {%1, %2, %3, %4}, [%17];\n"
                           "@p1 ld.relaxed.gpu.global.v4.u32 {%5, %6, %7, %8}, [%17 + 8192];\n"
                           "@p2 ld.relaxed.gpu.global.v4.u32 {%9, %10, %11, %12}, [%18];\n"
                           "@p3 ld.relaxed.gpu.global.v4.u32 {%13, %14, %15, %16}, [%18 + 128];\n"
                           "or.pred p0, p0, p1; or.pred p2, p2, p3; vote.sync.any.pred p0, p0, 0xffffffff; vote.sync.any.pred p2, p2, 0xffffffff;\n"
                           "selp.u32 t, 1, 0, p0; selp.u32 u, 2, 0, p2; or.b32 %0, t, u; }"
                           : "=r"(miss), "+r"(m0.x), "+r"(m0.y), "+r"(m0.z), "+r"(m0.w), "+r"(m1.x), "+r"(m1.y), "+r"(m1.z), "+r"(m1.w),
                             "+r"(r0.x), "+r"(r0.y), "+r"(r0.z), "+r"(r0.w), "+r"(r1.x), "+r"(r1.y), "+r"(r1.z), "+r"(r1.w)
                           : "l"(pm), "l"(pr), "r"(tag) : "memory");
              if (!(miss & 1) && !written) {
                written = true;
                if (!oddw) write_table(par, wg, t7, m0, m1);
                mbar_arrive(bar_mod);
              }
              if (!miss) break;
              watchdog(n);
            }
          }
          const uint32_t zero = r0.w ^ tag;
          auto normalize = [&](uint32_t (&f)[16]) {
#pragma unroll
            for (int k = 0; k < 16; k += 2) { f[k] = ln_norm(f[k], r0.x, r0.y, r0.z); f[k + 1] = ln_norm(f[k + 1], r1.x, r1.y, r1.z); }
          };
          auto modulate = [&](int i, uint32_t (&f)[16]) {
#pragma unroll
            for (int kk = 0; kk < 4; kk++) {
              const uint4 m = lds4(mt + slice_of(i) * 256 + kk * 64);
              f[4 * kk] = hfma2(f[4 * kk], m.x, m.z); f[4 * kk + 1] = hfma2(f[4 * kk + 1], m.x, m.z);
              f[4 * kk + 2] = hfma2(f[4 * kk + 2], m.y, m.w); f[4 * kk + 3] = hfma2(f[4 * kk + 3], m.y, m.w);
            }
            keep(f);
            mbar_arrive_pred(xempty + (i & 3) * 8, l == 0);
          };
          auto publish = [&](int u, uint32_t (&f)[16]) {
#pragma unroll
            for (int kk = 0; kk < 4; kk++) stmatrix4(fa[kk] + OFF_STAGE + u * UNIT, f[4 * kk], f[4 * kk + 1], f[4 * kk + 2], f[4 * kk + 3]);
            __syncwarp();
            mbar_arrive_pred(bar_hpub + u * 8, l == 0);
          };
          auto multiply = [&](int i, uint32_t (&f)[16]) {
            mbar_wait(gfull + (i & 3) * 8, i >> 2);
            const uint64_t db = make_desc(base + (i & 3) * GST_BYTES + UNIT, 8192, 1024);
            wg_fence();
#pragma unroll
            for (int kk = 0; kk < 4; kk++) mma256_rs(ga, gb, f[4 * kk], f[4 * kk + 1], f[4 * kk + 2], f[4 * kk + 3], db + kk * 128);
            wg_commit();
          };
          auto next = [&](int i, uint32_t (&f)[16]) {
            wg_wait<1>();
            mbar_arrive_cl(rempty, GE + ((i + 2) & 3) * 8);
            uint32_t z = zero;
#pragma unroll
            for (int k = 0; k < 16; k += 2) asm volatile("lop3.b32 %0, %1, %2, %0, 0xA8;" : "+r"(z) : "r"(f[k]), "r"(f[k + 1]));
            fetch(i, f, z);
            normalize(f);
            if (i == 2) { keep(f); mbar_wait(bar_mod2, 0); }
            modulate(i, f); multiply(i, f);
          };
          normalize(a[0]); normalize(a[1]);
          keep(a[0]); keep(a[1]);
          mbar_wait(bar_mod, 0);
          PROF(1, tid == 0, 2);
          modulate(0, a[0]); multiply(0, a[0]); publish(0, a[0]);
          modulate(1, a[1]); multiply(1, a[1]);
#pragma unroll 1
          for (int i = 2; i < NRS; i += 2) {
            next(i, a[0]);
            if (i == 2) publish(1, a[0]);
            next(i + 1, a[1]);
          }
          wg_wait<1>();
          mbar_arrive_cl(rempty, GE + ((NRS + 2) & 3) * 8);
#pragma unroll 1
          for (int i = NRS; i < 14; i++) {
            mbar_wait(xfull + (i & 3) * 8, (i >> 2) & 1);
            mbar_wait(gfull + (i & 3) * 8, (i >> 2) & 1);
            const uint32_t xa = base + (i & 3) * GST_BYTES;
            const uint64_t da = make_desc(xa + wg * 8192, 16, 1024), db = make_desc(xa + UNIT, 8192, 1024);
            if (i == 13) bar_sync(2 + wg, 256);
            wg_fence();
#pragma unroll
            for (int kk = 0; kk < 4; kk++) mma256_ss(ga, gb, da + kk * 2, db + kk * 128, 1);
            wg_commit();
            if (i == 13) bar_arrive(3 - wg, 256);
            wg_wait<1>();
            uint32_t z = zero;
#pragma unroll
            for (int k = 0; k < 16; k += 2) asm volatile("lop3.b32 %0, %1, %2, %0, 0xA8;" : "+r"(z) : "r"(a[1][k]), "r"(a[1][k + 1]));
            mbar_arrive_cl(rempty, GE + ((i + 3) & 3) * 8 + z);
            mbar_arrive_pred(xempty + ((i + 3) & 3) * 8, l == 0 && i != NRS);
          }
          mbar_wait(xfull + 16, 1);
          wg_wait<0>();
          keep(ga); keep(gb);
#pragma unroll
          for (int i = 0; i < 64; i++) {
            asm volatile("mov.b32 %0, %1;" : "=f"(s[i]) : "f"(ga[i]));
            asm volatile("mov.b32 %0, %1;" : "=f"(o[i]) : "f"(gb[i]));
          }
        } else {
          float ga[64], gb[64];
#pragma unroll
          for (int i = 0; i < 64; i++) {
            asm volatile("mov.b32 %0, %1;" : "=f"(ga[i]) : "f"(s[i]));
            asm volatile("mov.b32 %0, %1;" : "=f"(gb[i]) : "f"(o[i]));
          }
#pragma unroll 1
          for (int i = 0; i < nst; i++) {
            mbar_wait(gfull + (i & 3) * 8, (i >> 2) & 1);
            const uint64_t da = make_desc(base + unit_of(xt, i & 3) + wg * 8192, 16, 1024), db = make_desc(base + unit_of(wt, i & 3), 8192, 1024);
            if (i == nst - 1) bar_sync(2 + wg, 256);
            wg_fence();
#pragma unroll
            for (int kk = 0; kk < 4; kk++) mma256_ss(ga, gb, da + kk * 2, db + kk * 128, kk ? 1 : i);
            wg_commit();
            if (i == nst - 1) bar_arrive(3 - wg, 256);
            wg_wait<1>();
            mbar_arrive_cl(rempty, GE + ((i + 3) & 3) * 8, i != 0);
            PROF(4, tid == 0 && (i & 3) == 0, 40 + (ps - 1) * 4 + i / 4);
          }
          wg_wait<0>();
          keep(ga); keep(gb);
#pragma unroll
          for (int i = 0; i < 64; i++) {
            asm volatile("mov.b32 %0, %1;" : "=f"(s[i]) : "f"(ga[i]));
            asm volatile("mov.b32 %0, %1;" : "=f"(o[i]) : "f"(gb[i]));
          }
        }
        mbar_arrive_cl(rempty, GE + (ps == 2 ? 24 : 8));
        if (ps == 2) break;
      }
      const uint32_t qw = base + wg * 8192, qt = QT >> (16 * ps), at = ps ? AT1 : AT0;
      {
        const uint32_t wt = ps ? WT1 : WT0;
        const uint64_t da0 = make_desc(qw + unit_of(qt, 2), 16, 1024), da1 = make_desc(qw + unit_of(qt, 3), 16, 1024);
        const uint64_t db0 = make_desc(base + unit_of(wt, 2), 8192, 1024), db1 = make_desc(base + unit_of(wt, 3), 8192, 1024);
        mbar_wait(gfull + 16, 1);
        bar_sync(2 + wg, 256);
        wg_fence();
#pragma unroll
        for (int kk = 0; kk < 4; kk++) mma_ss<1>(s, da0 + kk * 2, db0 + kk * 128, 1);
        wg_commit();
        mbar_wait(xfull + 24, 1);
        mbar_wait(gfull + 24, 1);
        wg_fence();
#pragma unroll
        for (int kk = 0; kk < 4; kk++) mma_ss<1>(s, da1 + kk * 2, db1 + kk * 128, 1);
        wg_commit();
        bar_arrive(3 - wg, 256);
        mbar_wait(ps == 0 ? bar_pread : bar_ofree + 8, 0);
        wg_wait<0>();
        keep(s);
        PROF(2, tid == 0, 8 + ps * 8);
        uint32_t q[32];
        pack_p(s, q);
#pragma unroll
        for (int i = 0; i < 4; i++) stmatrix4((qw + unit_of(qt, 0) + frag_offset(warp)) ^ (i << 5), q[4 * i], q[4 * i + 1], q[4 * i + 2], q[4 * i + 3]);
        keep(q);
        bar_sync(2 + wg, 256);
        wg_fence();
#pragma unroll
        for (int kk = 0; kk < 8; kk++) mma_ss<1>(o, (kk < 4 ? da0 : da1) + (kk & 3) * 2, (kk < 4 ? db0 : db1) + UNIT / 16 + (kk & 3) * 128, 1);
        wg_commit();
        mbar_wait(bfull, 0);
        wg_fence();
        const uint64_t dk = make_desc(base + unit_of(at, 0), 16, 1024);
#pragma unroll
        for (int kk = 0; kk < 8; kk++) mma_rs<0>(s, q[4 * kk], q[4 * kk + 1], q[4 * kk + 2], q[4 * kk + 3], dk + (kk >> 2) * 1024 + (kk & 3) * 2, kk != 0);
        wg_commit();
        bar_arrive(3 - wg, 256);
#pragma unroll
        for (int i = 4; i < 8; i++) stmatrix4((qw + unit_of(qt, 1) + frag_offset(warp)) ^ ((i & 3) << 5), q[4 * i], q[4 * i + 1], q[4 * i + 2], q[4 * i + 3]);
        wg_wait<1>();
        keep(o);
        mbar_arrive_cl(rempty, GE + 16);
        mbar_arrive_cl(rempty, GE + 24);
        store_chunk<0>(o, qw + unit_of(qt, 2) + frag_offset(warp));
        store_chunk<1>(o, qw + unit_of(qt, 3) + frag_offset(warp));
        wg_wait<0>();
        keep(s);
        mbar_arrive_cl(rempty, 0);
      }
      PROF(4, tid == 0 && ps == 1, 61);
      float l0 = 0.f, l1 = 0.f;
      auto step = [&](auto odd_c, const int j, uint32_t (&pw)[32], uint32_t (&pr)[32]) {
        constexpr bool ODD = decltype(odd_c)::value;
        const bool first = !ODD && (j & 2) == 0, last = ODD && j == 7;
        const uint32_t ph = (j >> 1) & 1;
        float i0, i1, a0, a1;
        const bool so = !ODD && j == 4;
        if (so) { i0 = inv_quad_sum(l0); i1 = inv_quad_sum(l1); l0 = 0.f; l1 = 0.f; }
        bool redo = !ODD && (j | ps) == 0;
        while (true) {
          if (redo) {
            float m0 = fmaxf(s[0], s[1]), m1 = fmaxf(s[2], s[3]);
#pragma unroll
            for (int i = 1; i < 16; i++) { m0 = fmaxf(m0, fmaxf(s[4 * i], s[4 * i + 1])); m1 = fmaxf(m1, fmaxf(s[4 * i + 2], s[4 * i + 3])); }
            m0 = fmaxf(m0, __shfl_xor_sync(0xffffffffu, m0, 1)); m1 = fmaxf(m1, __shfl_xor_sync(0xffffffffu, m1, 1));
            m0 = fmaxf(m0, __shfl_xor_sync(0xffffffffu, m0, 2)); m1 = fmaxf(m1, __shfl_xor_sync(0xffffffffu, m1, 2));
            m0 *= SCL2; m1 *= SCL2;
            if (!first) {
              m0 = fmaxf(m0, f0); m1 = fmaxf(m1, f1);
              const float c0 = ex2(f0 - m0), c1 = ex2(f1 - m1);
              l0 *= c0; l1 *= c1;
              wg_wait<0>();
              keep(o);
#pragma unroll
              for (int i = 0; i < 16; i++) { o[4 * i] *= c0; o[4 * i + 1] *= c0; o[4 * i + 2] *= c1; o[4 * i + 3] *= c1; }
            }
            f0 = m0; f1 = m1;
          }
          float b0 = 0.f, b1 = 0.f;
          a0 = 0.f; a1 = 0.f;
#pragma unroll
          for (int i = 0; i < 16; i++) {
            const float e0 = ex2(fmaf(s[4 * i], SCL2, -f0)), e1 = ex2(fmaf(s[4 * i + 1], SCL2, -f0));
            const float e2 = ex2(fmaf(s[4 * i + 2], SCL2, -f1)), e3 = ex2(fmaf(s[4 * i + 3], SCL2, -f1));
            a0 += e0; b0 += e1; a1 += e2; b1 += e3;
            pw[2 * i] = pack_bf(e0, e1); pw[2 * i + 1] = pack_bf(e2, e3);
            if (i == VREL) {
#pragma unroll
              for (int k = 0; k < 2 * VREL + 2; k++) asm volatile("" : "+r"(pw[k])::"memory");
              mbar_wait(bar_mod, 0);
              wg_wait<0>();
              mbar_arrive_cl(rempty, ODD ? 16 : 0, !redo && (ODD || j));
#pragma unroll
              for (int k = 4 * VREL + 4; k < 64; k++) asm volatile("" : "+f"(s[k])::"memory");
            }
          }
          a0 += b0; a1 += b1;
          if (redo) break;
          redo = __any_sync(0xffffffffu, !(a0 + a1 < 0x1p90f) || (!ODD && fminf(a0, a1) < (first ? 0x1p-90f : 0.f)));
          if (!redo) break;
        }
        l0 += a0; l1 += a1;
        keep(pw);
        keep(o);
        if (so) store_chunk<0>(o, i0, i1, qw + unit_of(qt, 0) + frag_offset(warp));
        keep(o);
        if (j == (ODD ? 5 : 0)) { fence_async_smem(); if (ODD) mbar_arrive(bar_ofull + wg * 8); }
        mbar_wait(bfull + (ODD ? 24 : 8), ph);
        bar_sync(2 + wg, 256);
        if (!last) {
          const uint32_t qn = qt >> (j >= 3 ? 8 : 0);
          wg_fence();
          issue_qk(s, qw + unit_of(qn, 0), qw + unit_of(qn, 1), base + unit_of(at, ODD ? 3 : 1));
          wg_commit();
          mbar_wait(bfull + (ODD ? 0 : 16), ODD ? ph ^ 1 : ph);
        }
        if (so) { store_chunk<1>(o, i0, i1, qw + unit_of(qt, 1) + frag_offset(warp)); keep(o); }
        wg_fence();
        issue_pv(o, pw, base + unit_of(at, ODD ? (last ? 3 : 0) : 2), !first);
        wg_commit();
        bar_arrive(3 - wg, 256);
        wg_wait<1>();
        keep(s);
        mbar_arrive_cl(rempty, ODD ? 24 : 8, !last);
        PROF(4, tid == 0 && ps == 1, 51 + j);
      };
      uint32_t pa[32], pb[32];
#pragma unroll 1
      for (int j = 0; j < 8; j += 2) {
        step(std::false_type{}, j, pa, pb);
        step(std::true_type{}, j + 1, pb, pa);
      }
      {
        const float i0 = inv_quad_sum(l0), i1 = inv_quad_sum(l1);
        wg_wait<0>();
        keep(o);
        mbar_arrive_cl(rempty, 24);
        store_chunk<0>(o, i0, i1, qw + unit_of(qt, 2) + frag_offset(warp));
        store_chunk<1>(o, i0, i1, qw + unit_of(qt, 3) + frag_offset(warp));
        fence_async_smem();
        mbar_arrive(bar_ofull + 16 + wg * 8);
      }
      PROF(2, tid == 0, 10 + ps * 8);
    }

    const int ln = fresh_lane(), g = ln >> 2, tq = ln & 3, ct = warp * 32 + ln;
    const bool lane0 = ln == 0;
    const int lrow0 = warp * 16 + g;
    const uint32_t res = base + OFF_RES, trow = res + wg * 8192 + frag_offset(warp);
    uint32_t xr[32];
    uint4 sv[4], own;
    uint32_t* const sg = g_stats + (rb * 8 + warp) * 512 + g * 4;
    uint32_t* sp[4];
#pragma unroll
    for (int k = 0; k < 4; k++) sp[k] = sg + (tq & 1) * 32 + (((tq >> 1) ^ (cj >> 2)) * 4 + (k ^ (cj & 3))) * 64;
    {
      const uint64_t da = make_desc(base + wg * 8192, 16, 1024), db = make_desc(base, 8192, 1024);
      constexpr int U = UNIT / 16;
#define HALF_STAGE(acc, xu, wu) _Pragma("unroll") for (int kk = 0; kk < 4; kk++) mma_ss<1>(acc, da + (xu) * U + kk * 2, db + (wu) * U + kk * 128, 1)
      PROF(10, ct == PT, 19); STAMP(0);
      cluster_arrive();
      mbar_wait(gfull, 1);
      mbar_wait(gfull + 8, 1);
      bar_sync(2 + wg, 256);
      wg_fence();
      HALF_STAGE(o, 7, 1);
      HALF_STAGE(o, 8, 3);
      wg_commit();
      STAMP(16);
      mbar_wait(gfull + 16, 1);
      STAMP(17);
      wg_fence();
      HALF_STAGE(o, 6, 11);
      wg_commit();
      bar_arrive(3 - wg, 256);
      mbar_wait(bar_par, 0);
      uint32_t* xo = g_xch + ((size_t)b * 8 * 256 + ct) * 4;
      const uint32_t* xi = g_xch + ((size_t)(b ^ 2) * 8 * 256 + ct) * 4;
      const uint32_t par1 = (~lds1(par + PAR_CONST + 4) & 1) << 16;
      wg_wait<1>();
      mbar_arrive_pred(bar_rel, lane0);
      wg_wait<0>();
      keep(o);
      mbar_arrive_pred(bar_ring, lane0);
      PROF(8, ct == PT, 20); STAMP(1);
#define SEND(i) st_b128(xo + (i) * 1024, (pack_bf(o[8 * (i)], o[8 * (i) + 1]) & ~0x10000u) | par1, pack_bf(o[8 * (i) + 2], o[8 * (i) + 3]), \
                        pack_bf(o[8 * (i) + 4], o[8 * (i) + 5]), pack_bf(o[8 * (i) + 6], o[8 * (i) + 7]))
#pragma unroll
      for (int i = 0; i < NS1; i++) SEND(i);
      PROF(8, ct == PT, 21); STAMP(2);
      bar_sync(2 + wg, 256);
      wg_fence();
      HALF_STAGE(s, 7, 0);
      HALF_STAGE(s, 8, 2);
      HALF_STAGE(s, 6, 10);
      wg_commit();
      bar_arrive(3 - wg, 256);
      STAMP(18);
      mbar_wait(gfull + 24, 1);
#pragma unroll
      for (int i = NS1; i < 8; i++) SEND(i);
      uint4 v[8];
      STAMP(19);
      mbar_wait(bar_xres, 0);
      wg_wait<0>();
      mbar_arrive_pred(bar_ring + 8, lane0);
      bar_sync(2 + wg, 256);
      STAMP(20);
#pragma unroll
      for (int i = 0; i < LD2; i++) v[i] = ld_b128(xi + i * 1024);
      mbar_wait(bar_xres, 0);
      wg_fence();
      HALF_STAGE(s, 9, 4);
      wg_commit();
      mbar_wait(bar_rx, 0);
      wg_fence();
      HALF_STAGE(s, 1, 5);
      wg_commit();
      bar_arrive(3 - wg, 256);
      STAMP(21);
#pragma unroll
      for (int i = LD2; i < 8; i++) v[i] = ld_b128(xi + i * 1024);
      mbar_wait(bar_xres, 0);
      wg_wait<0>();
      keep(s);
      mbar_arrive_pred(bar_ring + 16, lane0);
      PROF(10, ct == PT, 23); STAMP(4);
#pragma unroll
      for (int i = 0; i < 16; i += 2) ldmatrix4((trow ^ ((i & 7) << 4)) + (i >> 3) * 16384, xr[2 * i], xr[2 * i + 1], xr[2 * i + 2], xr[2 * i + 3]);
      uint32_t ga[16];
      uint4 bw[8];
#pragma unroll
      for (int i = 0; i < 8; i++) {
        if (!(i & 1)) {
          const uint4 t = lds4(par + PAR_SINK + i * 32 + tq * 16);
          ga[2 * i] = t.x; ga[2 * i + 1] = t.y; ga[2 * i + 2] = t.z; ga[2 * i + 3] = t.w;
        }
        bw[i] = lds4(par + PAR_T1 + i * 64 + tq * 16);
        if (!(g & 1)) { bw[i].x = 0x3f803f80u; bw[i].y = 0x3f803f80u; }
      }
      uint32_t pk[32];
      pack_p(s, pk);
      uint32_t z = lds1(par + PAR_CONST + 48);
#define ZMASK(a, c) asm volatile("lop3.b32 %0, %1, %2, %0, 0xA8;" : "+r"(z) : "r"(a), "r"(c))
      if (ZM) {
#pragma unroll
        for (int i = 0; i < 16; i++) ZMASK(pk[2 * i], pk[2 * i + 1]);
#pragma unroll
        for (int i = 0; i < 8; i++) ZMASK(bw[i].x, bw[i].y);
#pragma unroll
        for (int i = 0; i < 4; i++) ZMASK(ga[4 * i], xr[8 * i + 4]);
      }
      const uint32_t par2 = par1 ^ z;
      {
        uint32_t n = 0, miss;
        do {
          miss = 0;
#pragma unroll
          for (int i = 0; i < 8; i++) miss |= v[i].x ^ par2;
          miss = __any_sync(0xffffffffu, miss & 0x10000u);
          if (miss) {
#pragma unroll
            for (int i = 0; i < 8; i++)
              asm volatile("{ .reg .pred p; .reg .b32 t; xor.b32 t, %0, %5; and.b32 t, t, 0x10000; setp.ne.u32 p, t, 0;\n"
                           "@p ld.relaxed.gpu.global.v4.u32 {%0, %1, %2, %3}, [%4]; }"
                           : "+r"(v[i].x), "+r"(v[i].y), "+r"(v[i].z), "+r"(v[i].w) : "l"(xi + i * 1024), "r"(par1) : "memory");
          }
          watchdog(n);
        } while (miss);
      }
      PROF(8, ct == PT, 22); STAMP(3);
      float ds[4] = {0.f, 0.f, 0.f, 0.f}, dl[4] = {0.f, 0.f, 0.f, 0.f}, q0[4] = {0.f, 0.f, 0.f, 0.f}, q1[4] = {0.f, 0.f, 0.f, 0.f};
#pragma unroll
      for (int i = 0; i < 8; i++) {
        const uint32_t u0 = hfma2(ga[2 * i], hadd2(pk[4 * i], v[i].x & ~0x10000u), xr[4 * i]);
        const uint32_t u1 = hfma2(ga[2 * i], hadd2(pk[4 * i + 1], v[i].y), xr[4 * i + 1]);
        const uint32_t u2 = hfma2(ga[2 * i + 1], hadd2(pk[4 * i + 2], v[i].z), xr[4 * i + 2]);
        const uint32_t u3 = hfma2(ga[2 * i + 1], hadd2(pk[4 * i + 3], v[i].w), xr[4 * i + 3]);
        xr[4 * i] = u0; xr[4 * i + 1] = u1; xr[4 * i + 2] = u2; xr[4 * i + 3] = u3;
        mma16816(ds, u0, u1, u2, u3, bw[i].x, bw[i].y);
        mma16816(dl, u0, u1, u2, u3, bw[i].z, bw[i].w);
        mma16816(q0, u0, u1, u2, u3, u0, u2);
        mma16816(q1, u0, u1, u2, u3, u1, u3);
      }
      const float sqa = (g & 1) ? q0[1] : q0[0], sqb = (g & 1) ? q1[3] : q1[2], dta = ds[1] + dl[1], dtb = ds[3] + dl[3];
      if (tq == (g >> 1)) {
        st_b128(sg + cj * 64, __float_as_uint(ds[0]), __float_as_uint(sqa), __float_as_uint(dta), tag);
        st_b128(sg + cj * 64 + 32, __float_as_uint(ds[2]), __float_as_uint(sqb), __float_as_uint(dtb), tag);
      }
#pragma unroll
      for (int k = 0; k < 4; k++) sv[k] = ld_b128(sp[k]);
      mbar_wait(bar_xres, 0);
      const float sqc = __shfl_sync(0xffffffffu, sqa, g * 4 + (g >> 1)), sqd = __shfl_sync(0xffffffffu, sqb, g * 4 + (g >> 1));
      own = (tq & 1) ? make_uint4(__float_as_uint(ds[2]), __float_as_uint(sqd), __float_as_uint(dtb), tag)
                     : make_uint4(__float_as_uint(ds[0]), __float_as_uint(sqc), __float_as_uint(dta), tag);
    }
    PROF(8, ct == PT, 29); STAMP(5);
    uint32_t mm, ih, il;
    float rbest;
    uint32_t wf[128];
    const uint32_t frow = (ln & 7) + (ln >> 4) * 8;
    const uint32_t wfo = base + (warp & 1) * 8192 + frow * 64 + ((((ln >> 3) & 1) ^ ((frow >> 1) & 3)) << 4);
#define LOAD_WF(m) _Pragma("unroll") for (int f = 0; f < 16; f++) {                                                   \
      const int r = ((f >> 1) * 4 + (m) * 2 + (f & 1)) * 4;                                                           \
      ldmatrix4t(((wfo + unit_of((m) ? FT_U : FT_G, warp >> 1)) ^ ((f & 1) * 32)) + (f >> 1) * 1024, wf[r], wf[r + 1], wf[r + 2], wf[r + 3]); \
    }
    bool early;
    {
#pragma unroll
      for (int i = 0; i < 16; i += 2) stmatrix4((trow ^ ((i & 7) << 4)) + (i >> 3) * 16384, xr[2 * i], xr[2 * i + 1], xr[2 * i + 2], xr[2 * i + 3]);
      const uint4 cst = lds4(par + PAR_CONST);
      const float A1 = __uint_as_float(cst.x), A2 = __uint_as_float(cst.z);
      uint32_t n = 0;
      early = false;
#pragma unroll 1
      while (true) {
        if (!early && (b >= NFFN || __all_sync(0xffffffffu, mbar_test(bar_box + (warp >> 1) * 8, 0)))) {
          early = true;
          LOAD_WF(0);
          __syncwarp();
          mbar_arrive_pred(bar_gate, lane0);
        }
        uint32_t miss;
        asm volatile("{ .reg .pred p0, p1, p2, p3; .reg .b64 u, v; .reg .b128 w;\n"
                     "setp.ge.u32 p0, %22, 2; setp.ne.and.u32 p0, %4, %21, p0; setp.ne.u32 p1, %8, %21; setp.ne.u32 p2, %12, %21; setp.ne.u32 p3, %16, %21;\n"
                     "@p0 ld.relaxed.gpu.global.v4.u32 {%1, %2, %3, %4}, [%17];\n"
                     "@p1 ld.relaxed.gpu.global.v4.u32 {%5, %6, %7, %8}, [%18];\n"
                     "@p2 ld.relaxed.gpu.global.v4.u32 {%9, %10, %11, %12}, [%19];\n"
                     "@p3 ld.relaxed.gpu.global.v4.u32 {%13, %14, %15, %16}, [%20];\n"
                     "or.pred p0, p0, p1; or.pred p2, p2, p3; or.pred p0, p0, p2; vote.sync.any.pred p0, p0, 0xffffffff; selp.u32 %0, 1, 0, p0; }"
                     : "=r"(miss), "+r"(sv[0].x), "+r"(sv[0].y), "+r"(sv[0].z), "+r"(sv[0].w), "+r"(sv[1].x), "+r"(sv[1].y), "+r"(sv[1].z), "+r"(sv[1].w),
                       "+r"(sv[2].x), "+r"(sv[2].y), "+r"(sv[2].z), "+r"(sv[2].w), "+r"(sv[3].x), "+r"(sv[3].y), "+r"(sv[3].z), "+r"(sv[3].w)
                     : "l"(sp[0]), "l"(sp[1]), "l"(sp[2]), "l"(sp[3]), "r"(tag), "r"(tq) : "memory");
        if (!miss) break;
        watchdog(n);
      }
      const uint4 v0 = tq < 2 ? own : sv[0], v1 = sv[1], v2 = sv[2], v3 = sv[3];
      PROF(8, ct == PT, 30); STAMP(6);
      float su = (__uint_as_float(v0.x) + __uint_as_float(v1.x)) + (__uint_as_float(v2.x) + __uint_as_float(v3.x));
      float sq = (__uint_as_float(v0.y) + __uint_as_float(v1.y)) + (__uint_as_float(v2.y) + __uint_as_float(v3.y));
      float dt = (__uint_as_float(v0.z) + __uint_as_float(v1.z)) + (__uint_as_float(v2.z) + __uint_as_float(v3.z));
      su += __shfl_xor_sync(0xffffffffu, su, 2); sq += __shfl_xor_sync(0xffffffffu, sq, 2); dt += __shfl_xor_sync(0xffffffffu, dt, 2);
      const float m = su * (1.f / DM);
      float mb, sd;
      ln_scalars(m, fmaxf(sq * (1.f / DM) - m * m, 0.f), mb, sd);
      const float inv = rcp(sd);
      rbest = (dt - mb * A1) * inv + A2;
      mm = pack_bf(mb, mb);
      ih = pack_bf(inv, inv);
      const float lo = inv - bf_lo(ih);
      il = pack_bf(lo, lo);
    }
    int ibest;
    {
      const uint32_t bits = __float_as_uint(rbest);
      const uint32_t key = (((int)bits < 0 ? ~bits : bits | 0x80000000u) & ~0x1ffu) | ((127 - lrow0 - (tq & 1) * 8) << 2) | tag;
      sts1(par + PAR_RED + warp * 4, __reduce_max_sync(0xffffffffu, key));
      PROF(8, ct == PT, 38); STAMP(7);
      bar_sync(1, 256);
      const uint4 ka = lds4(par + PAR_RED), kb = lds4(par + PAR_RED + 16);
      const uint32_t k2 = max(max(max(ka.x, ka.y), max(ka.z, ka.w)), max(max(kb.x, kb.y), max(kb.z, kb.w)));
      if (ct < CR && cj == 0) st_relaxed(g_cand + ct * 512 + rb * CS, k2);
      ibest = 127 - ((k2 >> 2) & 127);
    }
    PROF(8, ct == PT, 39); STAMP(8);
    if ((ibest >> 4) == warp) {
      const int src = (ibest & 7) * 4 + ((ibest >> 3) & 1), ch = g * 2;
      const uint32_t cm = __shfl_sync(0xffffffffu, mm, src), ch_ = __shfl_sync(0xffffffffu, ih, src), cl = __shfl_sync(0xffffffffu, il, src);
      const uint32_t xa = res + (ch >> 3) * 16384 + ibest * 128 + (((ch & 7) ^ (ibest & 7)) << 4) + tq * 4;
      const uint32_t x0 = lds1(xa), x1 = lds1(xa ^ 16);
      const uint2 p0 = lds2(par + PAR_T2 + ch * 64 + tq * 16), p1 = lds2(par + PAR_T2 + ch * 64 + 64 + tq * 16);
      uint32_t* dst = g_row + rb * 2 * DM + cj * 128 + ln * 4;
      st_pairs(dst, ln_mod(x0, cm, ch_, cl, p0.x, p0.y), ln_mod(x1, cm, ch_, cl, p1.x, p1.y), tag);
      st_pairs(dst + DM, x0, x1, tag);
      __syncwarp();
    }
    PROF(8, ct == PT, 37); STAMP(9);
    uint32_t wd[64];
    const uint32_t wda = base + unit_of(FT_D, warp >> 1) + (warp & 1) * 8192 + frow * 128 + ((((ln >> 3) & 1) ^ (ln & 7)) << 4);
#define LOAD_WD(f) ldmatrix4t((wda ^ ((((f) >> 1) & 3) * 32)) + ((f) >> 3) * 4096 + ((f) & 1) * 2048, wd[4 * (f)], wd[4 * (f) + 1], wd[4 * (f) + 2], wd[4 * (f) + 3])
    if (!early) {
      if (b < NFFN) mbar_wait(bar_box + (warp >> 1) * 8, 0);
      LOAD_WF(0);
      __syncwarp();
      mbar_arrive_pred(bar_gate, lane0);
    }
    if (b < NFFN) {
      const uint32_t own = base + unit_of(FT_G, warp >> 1) + (warp & 1) * 8192;
      mbar_wait(bar_box + (4 + (warp >> 1)) * 8, 0);
      LOAD_WF(1);
      uint32_t* const ydst = ypart_slot(b, warp * 16 + (tq & 1) * 8 + g);
      PROF(8, ct == PT, 31); STAMP(10);
      bool wdok;
      {
        uint32_t n = 0;
        while (!(wdok = __all_sync(0xffffffffu, mbar_test(bar_box + (8 + (warp >> 1)) * 8, 0))) && !__all_sync(0xffffffffu, mbar_test(bar_sel, 0))) watchdog(n);
      }
      if (wdok) {
#pragma unroll
        for (int f = 0; f < 16; f++) LOAD_WD(f);
      }
      STAMP(11);
      mbar_wait(bar_sel, 0);
      PROF(8, ct == PT, 33); STAMP(12);
      float d[8][4];
#pragma unroll
      for (int i = 0; i < 4; i++) { d[i][0] = 0.f; d[i][1] = 0.f; d[i][2] = 0.f; d[i][3] = 0.f; }
#pragma unroll
      for (int ks = 0; ks < 8; ks++) {
        const uint2 hb = lds2(own + 256 + ks * 32 + tq * 8);
#pragma unroll
        for (int mt = 0; mt < 4; mt++) {
          const int r = ks * 16 + mt * 4;
          mma16816(d[mt], wf[r], wf[r + 1], wf[r + 2], wf[r + 3], hb.x, hb.y);
        }
      }
      sts2(own + (tq * 8 + g) * 8, __float_as_uint((tq & 2) ? ((tq & 1) ? d[1][2] : d[1][0]) : ((tq & 1) ? d[0][2] : d[0][0])),
           __float_as_uint((tq & 2) ? ((tq & 1) ? d[3][2] : d[3][0]) : ((tq & 1) ? d[2][2] : d[2][0])));
      bar_sync(1, 256);
      uint32_t ab[4];
      {
        float G = 0.f, U = 0.f;
        uint2 pv[8];
#pragma unroll
        for (int w8 = 0; w8 < 8; w8++) pv[w8] = lds2(base + ln * 8 + ((FT_G >> (w8 >> 1) * 4) & 15) * UNIT + (w8 & 1) * 8192);
#pragma unroll
        for (int w8 = 0; w8 < 8; w8 += 2) {
          G += __uint_as_float(pv[w8].x) + __uint_as_float(pv[w8 + 1].x);
          U += __uint_as_float(pv[w8].y) + __uint_as_float(pv[w8 + 1].y);
        }
        const float act = rbf(silu_f(rbf(G))) * rbf(U);
        const uint32_t pk = pack_bf(act, __shfl_down_sync(0xffffffffu, act, 1));
#pragma unroll
        for (int i = 0; i < 4; i++) ab[i] = __shfl_sync(0xffffffffu, pk, i * 8 + tq * 2);
      }
      if (!wdok) {
        mbar_wait(bar_box + (8 + (warp >> 1)) * 8, 0);
#pragma unroll
        for (int f = 0; f < 16; f++) LOAD_WD(f);
      }
      PROF(8, ct == PT, 34); STAMP(13);
#pragma unroll
      for (int mt = 0; mt < 8; mt++) {
        d[mt][0] = 0.f; d[mt][1] = 0.f; d[mt][2] = 0.f; d[mt][3] = 0.f;
        mma16816(d[mt], wd[mt * 8], wd[mt * 8 + 1], wd[mt * 8 + 2], wd[mt * 8 + 3], ab[0], ab[1]);
        mma16816(d[mt], wd[mt * 8 + 4], wd[mt * 8 + 5], wd[mt * 8 + 6], wd[mt * 8 + 7], ab[2], ab[3]);
      }
      uint32_t yw[4];
#pragma unroll
      for (int i = 0; i < 4; i++) yw[i] = (tq & 1) ? pack_bf(d[2 * i][2], d[2 * i + 1][2]) : pack_bf(d[2 * i][0], d[2 * i + 1][0]);
      if (tq < 2) st_b128(ydst, (yw[0] & ~1u) | (tag & 1), (yw[1] & ~1u) | (tag >> 1), yw[2], yw[3]);
      PROF(8, ct == PT, 35); STAMP(14);
    }
    mbar_wait(bar_sel, 0);
    mbar_arrive_pred(bar_win, ct == 0);
    const int iwin = lds1(par + PAR_CONST + 60) & 0x7ff;
    const bool cand = (iwin >> 4) == rb * 8 + warp;
    {
      const uint32_t mm0 = __shfl_sync(0xffffffffu, mm, ln & ~1), mm1 = __shfl_sync(0xffffffffu, mm, ln | 1);
      const uint32_t ih0 = __shfl_sync(0xffffffffu, ih, ln & ~1), ih1 = __shfl_sync(0xffffffffu, ih, ln | 1);
      const uint32_t il0 = __shfl_sync(0xffffffffu, il, ln & ~1), il1 = __shfl_sync(0xffffffffu, il, ln | 1);
#pragma unroll 1
      for (int hf = 0; hf < 2; hf++) {
        uint32_t x[16];
#pragma unroll
        for (int i = 0; i < 8; i += 2) ldmatrix4((trow ^ (i << 4)) + hf * 16384, x[2 * i], x[2 * i + 1], x[2 * i + 2], x[2 * i + 3]);
#pragma unroll
        for (int i = 0; i < 8; i++) {
          const uint4 pv = lds4(par + PAR_T2 + (hf * 8 + i) * 64 + tq * 16);
          x[2 * i] = hfma2(hfma2(ln_norm(x[2 * i], mm0, ih0, il0), pv.x, pv.y), pv.z, x[2 * i]);
          x[2 * i + 1] = hfma2(hfma2(ln_norm(x[2 * i + 1], mm1, ih1, il1), pv.x, pv.y), pv.z, x[2 * i + 1]);
        }
#pragma unroll
        for (int i = 0; i < 8; i += 2) stmatrix4((trow ^ (i << 4)) + hf * 16384, x[2 * i], x[2 * i + 1], x[2 * i + 2], x[2 * i + 3]);
        if (!cand) fence_async_smem();
        __syncwarp();
        if (!cand && elect_one()) {
          tma2d_store(&maps.out, res + hf * 16384 + warp * 2048, cj * 128 + hf * 64, rb * 128 + warp * 16);
          asm volatile("cp.async.bulk.commit_group;" ::: "memory");
        }
      }
    }
    if (cand) {
      const int wrow0 = warp * 16;
#pragma unroll 2
      for (int p = 0; p < 8; p++) {
        const int row = 2 * p + (ln >> 4), ch = ln & 15;
        const uint4 v = lds4(res + (ch >> 3) * 16384 + (wrow0 + row) * 128 + (((ch & 7) ^ (row & 7)) << 4));
        if (rb * 128 + wrow0 + row != iwin) *reinterpret_cast<uint4*>(P.out + (size_t)(rb * 128 + wrow0 + row) * DM + cj * 128 + ch * 8) = v;
      }
    }
    asm volatile("cp.async.bulk.wait_group.read 0;" ::: "memory");
    PROF(8, ct == PT, 11); STAMP(15);
    cluster_wait();
  }
}

typedef CUresult (*EncodeFn)(CUtensorMap*, CUtensorMapDataType, cuuint32_t, void*, const cuuint64_t*, const cuuint64_t*,
                             const cuuint32_t*, const cuuint32_t*, CUtensorMapInterleave, CUtensorMapSwizzle,
                             CUtensorMapL2promotion, CUtensorMapFloatOOBfill);

void map2d(EncodeFn enc, CUtensorMap* m, const void* p, uint64_t rows, uint64_t cols, uint32_t brows) {
  cuuint64_t dims[2] = {cols, rows}, strides[1] = {cols * 2};
  cuuint32_t box[2] = {64, brows}, es[2] = {1, 1};
  enc(m, CU_TENSOR_MAP_DATA_TYPE_BFLOAT16, 2, const_cast<void*>(p), dims, strides, box, es, CU_TENSOR_MAP_INTERLEAVE_NONE,
      CU_TENSOR_MAP_SWIZZLE_128B, CU_TENSOR_MAP_L2_PROMOTION_L2_256B, CU_TENSOR_MAP_FLOAT_OOB_FILL_NONE);
}
void map2d_narrow(EncodeFn enc, CUtensorMap* m, const void* p, uint64_t rows, uint64_t cols, uint32_t brows) {
  cuuint64_t dims[2] = {cols, rows}, strides[1] = {cols * 2};
  cuuint32_t box[2] = {32, brows}, es[2] = {1, 1};
  enc(m, CU_TENSOR_MAP_DATA_TYPE_BFLOAT16, 2, const_cast<void*>(p), dims, strides, box, es, CU_TENSOR_MAP_INTERLEAVE_NONE,
      CU_TENSOR_MAP_SWIZZLE_64B, CU_TENSOR_MAP_L2_PROMOTION_L2_64B, CU_TENSOR_MAP_FLOAT_OOB_FILL_NONE);
}
void map3d(EncodeFn enc, CUtensorMap* m, const void* p, uint64_t rows, uint64_t cols, uint32_t brows, uint32_t nch) {
  cuuint64_t dims[3] = {64, rows, cols / 64}, strides[2] = {cols * 2, 128};
  cuuint32_t box[3] = {64, brows, nch}, es[3] = {1, 1, 1};
  enc(m, CU_TENSOR_MAP_DATA_TYPE_BFLOAT16, 3, const_cast<void*>(p), dims, strides, box, es, CU_TENSOR_MAP_INTERLEAVE_NONE,
      CU_TENSOR_MAP_SWIZZLE_128B, CU_TENSOR_MAP_L2_PROMOTION_L2_256B, CU_TENSOR_MAP_FLOAT_OOB_FILL_NONE);
}

}

extern "C" void kernel_launch(void* const* d_in, const int* in_sizes, int n_in, void* d_out, int out_size) {
  (void)in_sizes; (void)n_in; (void)out_size;
  static EncodeFn enc = nullptr;
  if (!enc) {
    void* fn = nullptr;
    cudaDriverEntryPointQueryResult st;
    cudaGetDriverEntryPoint("cuTensorMapEncodeTiled", &fn, cudaEnableDefault, &st);
    enc = (EncodeFn)fn;
    cudaFuncSetAttribute(fused_kernel, cudaFuncAttributeMaxDynamicSharedMemorySize, SMEM_BYTES);
  }
  Maps maps;
  map2d(enc, &maps.x, d_in[0], SEQ, DM, 128);
  map2d(enc, &maps.out, d_out, SEQ, DM, 16);
  map3d(enc, &maps.wq, d_in[3], DM, NQ, 64, 2);
  map3d(enc, &maps.k, d_in[1], 4 * SK, 128, 128, 1);
  map3d(enc, &maps.v, d_in[2], 4 * SK, 128, 128, 1);
  map3d(enc, &maps.wo, d_in[4], NQ, DM, 64, 2);
  map2d_narrow(enc, &maps.wg, d_in[7], DM, FF, 256);
  map2d_narrow(enc, &maps.wu, d_in[8], DM, FF, 256);
  map3d(enc, &maps.wd, d_in[9], FF, DM, 32, 4);
  map2d_narrow(enc, &maps.wm, d_in[11], DM, NMOD, 256);
  Ptrs p;
  p.x = (const __nv_bfloat16*)d_in[0];
  p.w_r = (const __nv_bfloat16*)d_in[6];
  p.w_gate = (const __nv_bfloat16*)d_in[7];
  p.w_up = (const __nv_bfloat16*)d_in[8];
  p.w_down = (const __nv_bfloat16*)d_in[9];
  p.c = (const __nv_bfloat16*)d_in[10];
  p.w_mod = (const __nv_bfloat16*)d_in[11];
  p.out = (__nv_bfloat16*)d_out;
  fused_kernel<<<NMAIN + NHELP, 384, SMEM_BYTES>>>(maps, p);
}
```

```cpp
#include <cuda_runtime.h>
#include <cuda_bf16.h>
#include <cuda.h>
#include <stdint.h>
#include <type_traits>

#define HD 2
#define HDX 2
#define NRS 8
#define OSL 900
#define OSL2 400
#define RSL 40
#define VREL 5
#define OPS 8192
#define ODS1 5
#define ODS 7
#define PG0 15
#define WB 2
#define WN 20
#define HU 32
#define RES0 17
#define RES1 20
#define GOST 20
#define NS1 5
#define LD2 4
#define FPACE0 2
#define FPACE 3
#define CR 8
#define CS 8

namespace {

constexpr int SEQ = 2048, DM = 1024, NQ = 4096, SK = 2048, WIN = 512, FF = 3584, NMOD = 6144;
constexpr int NMAIN = 128, NHELP = 4, NFFN = 112;
constexpr int NSLOT = 4, SLOT_BYTES = 32768, UNIT = 16384, GST_BYTES = 3 * UNIT;
constexpr uint32_t XT1 = 0xDCBA, XT2 = 0x9687;
constexpr uint32_t WT0 = 0xA741, WT1 = 0x7420, WT2 = 0x4A20;
constexpr uint32_t AT0 = WT1, AT1 = WT2;
constexpr uint32_t QT = 0xDC9696DC;
constexpr int OFF_STAGE = 12 * UNIT;
constexpr uint32_t FT_G = 0x07B3, FT_U = 0xA628, FT_D = 0x5149;
constexpr int OFF_RES = 12 * UNIT;
constexpr int OFF_PAR = 14 * UNIT;
constexpr int OFF_BAR = OFF_PAR + 2528;
constexpr int SMEM_BYTES = OFF_BAR + 544;
static_assert(SMEM_BYTES <= 232448, "smem");

constexpr int PAR_T1 = 0;
constexpr int PAR_T2 = 512;
constexpr int PAR_CONST = 1536;
constexpr int PAR_RED = 1600;
constexpr int PAR_SINK = 2176;

struct Maps {
  CUtensorMap x, wq, k, v, wo, wg, wu, wd, wm, out;
};
struct Ptrs {
  const __nv_bfloat16 *x, *w_r, *c, *w_mod, *w_gate, *w_up, *w_down;
  __nv_bfloat16* out;
};

__device__ __align__(1024) uint8_t g_act[16 * 80 * UNIT];
__device__ __align__(128) uint32_t g_mod[NMOD];
__device__ __align__(128) uint32_t g_modp[2 * 2 * DM];
__device__ __align__(128) uint32_t g_ln1[SEQ * 4];
__device__ __align__(128) uint32_t g_cnt_h[16 * 32];
__device__ __align__(128) uint32_t g_cnt_o[128 * 32];
__device__ __align__(128) uint32_t g_xch[NMAIN * 8 * 256 * 4];
__device__ __align__(128) uint32_t g_stats[8 * SEQ * 4];
__device__ __align__(128) uint32_t g_cand[CR * 512];
__device__ __align__(128) uint32_t g_row[16 * 2 * DM];
__device__ __align__(128) uint32_t g_ypart[NMAIN * NFFN * 4];
__device__ __forceinline__ uint32_t* ypart_slot(int writer, int reader) { return g_ypart + (writer * NMAIN + reader) * 4; }
__device__ uint32_t g_epoch;

__device__ __forceinline__ uint32_t fresh_lane() { uint32_t l; asm volatile("mov.u32 %0, %%laneid;" : "=r"(l)); return l; }
__device__ __forceinline__ uint32_t frag_offset(int warp) {
  const uint32_t l = fresh_lane();
  return ((warp & 3) * 16 + (l & 15)) * 128 + (((l >> 4) ^ (l & 7)) << 4);
}
__device__ __forceinline__ bool elect_one() {
  uint32_t p;
  asm volatile("{ .reg .pred q; elect.sync _|q, 0xffffffff; selp.u32 %0, 1, 0, q; }" : "=r"(p));
  return p;
}
__device__ __forceinline__ uint32_t smem_u32(const void* p) { return (uint32_t)__cvta_generic_to_shared(p); }
__device__ __forceinline__ void mbar_init(uint32_t bar, uint32_t cnt) {
  asm volatile("mbarrier.init.shared::cta.b64 [%0], %1;" ::"r"(bar), "r"(cnt) : "memory");
}
__device__ __forceinline__ void mbar_expect_tx(uint32_t bar, uint32_t bytes) {
  asm volatile("mbarrier.arrive.expect_tx.shared::cta.b64 _, [%0], %1;" ::"r"(bar), "r"(bytes) : "memory");
}
__device__ __forceinline__ void mbar_arrive(uint32_t bar) {
  asm volatile("mbarrier.arrive.shared::cta.b64 _, [%0];" ::"r"(bar) : "memory");
}
__device__ __forceinline__ void mbar_arrive_pred(uint32_t bar, bool p) {
  asm volatile("{ .reg .pred p; setp.ne.b32 p, %1, 0; @p mbarrier.arrive.shared::cta.b64 _, [%0]; }" ::"r"(bar), "r"((int)p) : "memory");
}
__device__ __forceinline__ void mbar_arrive_cl(uint32_t bar, uint32_t off, bool p = true) {
  asm volatile("{ .reg .pred p, q; .reg .b32 a; setp.ne.b32 q, %2, 0; setp.ne.and.b32 p, %0, 0, q; add.u32 a, %0, %1; @p mbarrier.arrive.shared::cluster.b64 _, [a]; }"
               ::"r"(bar), "r"(off), "r"((int)p) : "memory");
}
__device__ __forceinline__ uint32_t mapa(uint32_t addr, uint32_t cta) {
  uint32_t r; asm("mapa.shared::cluster.u32 %0, %1, %2;" : "=r"(r) : "r"(addr), "r"(cta)); return r;
}
__device__ __forceinline__ void cluster_arrive() { asm volatile("barrier.cluster.arrive.relaxed.aligned;" ::: "memory"); }
__device__ __forceinline__ void cluster_wait() { asm volatile("barrier.cluster.wait.aligned;" ::: "memory"); }
__device__ __forceinline__ void watchdog(uint32_t& n) {
}
__device__ __forceinline__ void mbar_wait(uint32_t bar, uint32_t parity) {
  asm volatile("{\n.reg .pred p;\nWAIT_%=:\nmbarrier.try_wait.parity.shared::cta.b64 p, [%0], %1;\n@!p bra WAIT_%=;\n}" ::"r"(bar), "r"(parity) : "memory");
}
__device__ __forceinline__ bool mbar_test(uint32_t bar, uint32_t parity) {
  uint32_t ok;
  asm volatile("{\n.reg .pred p;\nmbarrier.test_wait.parity.shared::cta.b64 p, [%1], %2;\nselp.u32 %0, 1, 0, p;\n}" : "=r"(ok) : "r"(bar), "r"(parity) : "memory");
  return ok;
}
__device__ __forceinline__ uint64_t l2_stream() {
  uint64_t f; asm("createpolicy.fractional.L2::evict_first.b64 %0, 1.0;" : "=l"(f)); return f;
}
__device__ __forceinline__ uint64_t l2_normal() {
  uint64_t f; asm("createpolicy.fractional.L2::evict_normal.b64 %0, 1.0;" : "=l"(f)); return f;
}
__device__ __forceinline__ void tma2d(uint32_t dst, const CUtensorMap* m, int c0, int c1, uint32_t bar) {
  asm volatile("cp.async.bulk.tensor.2d.shared::cluster.global.mbarrier::complete_tx::bytes.L2::cache_hint [%0], [%1, {%3, %4}], [%2], %5;"
               ::"r"(dst), "l"(m), "r"(bar), "r"(c0), "r"(c1), "l"(l2_stream()) : "memory");
}
__device__ __forceinline__ void bulk_load(uint32_t dst, const void* src, uint32_t bytes, uint32_t bar) {
  asm volatile("cp.async.bulk.shared::cluster.global.mbarrier::complete_tx::bytes [%0], [%1], %2, [%3];" ::"r"(dst), "l"(src), "r"(bytes), "r"(bar) : "memory");
}
__device__ __forceinline__ void bulk_load_stream(uint32_t dst, const void* src, uint32_t bytes, uint32_t bar, uint64_t pol = l2_stream()) {
  asm volatile("cp.async.bulk.shared::cluster.global.mbarrier::complete_tx::bytes.L2::cache_hint [%0], [%1], %2, [%3], %4;"
               ::"r"(dst), "l"(src), "r"(bytes), "r"(bar), "l"(pol) : "memory");
}
__device__ __forceinline__ void tma2d_store(const CUtensorMap* m, uint32_t src, int c0, int c1) {
  asm volatile("cp.async.bulk.tensor.2d.global.shared::cta.bulk_group [%0, {%2, %3}], [%1];" ::"l"(m), "r"(src), "r"(c0), "r"(c1) : "memory");
}
__device__ __forceinline__ void bulk_store(void* dst, uint32_t src, uint32_t bytes) {
  asm volatile("cp.async.bulk.global.shared::cta.bulk_group [%0], [%1], %2;" ::"l"(dst), "r"(src), "r"(bytes) : "memory");
}
__device__ __forceinline__ int slice_of(int i) { return i + ((i & 7) == 1) - ((i & 7) == 2); }
__device__ __forceinline__ uint32_t unit_of(uint32_t table, uint32_t i) { return ((table >> (i * 4)) & 15) * UNIT; }
__device__ __forceinline__ void tma3d(uint32_t dst, const CUtensorMap* m, int c0, int c1, int c2, uint32_t bar) {
  asm volatile("cp.async.bulk.tensor.3d.shared::cluster.global.mbarrier::complete_tx::bytes.L2::cache_hint [%0], [%1, {%3, %4, %5}], [%2], %6;"
               ::"r"(dst), "l"(m), "r"(bar), "r"(c0), "r"(c1), "r"(c2), "l"(l2_stream()) : "memory");
}
template <bool STREAM>
__device__ __forceinline__ void tma3d_mc(uint32_t dst, const CUtensorMap* m, int c0, int c1, int c2, uint32_t bar) {
  if (STREAM)
    asm volatile("cp.async.bulk.tensor.3d.shared::cluster.global.mbarrier::complete_tx::bytes.multicast::cluster.L2::cache_hint [%0], [%1, {%3, %4, %5}], [%2], %6, %7;"
                 ::"r"(dst), "l"(m), "r"(bar), "r"(c0), "r"(c1), "r"(c2), "h"((uint16_t)3), "l"(l2_stream()) : "memory");
  else
    asm volatile("cp.async.bulk.tensor.3d.shared::cluster.global.mbarrier::complete_tx::bytes.multicast::cluster [%0], [%1, {%3, %4, %5}], [%2], %6;"
                 ::"r"(dst), "l"(m), "r"(bar), "r"(c0), "r"(c1), "r"(c2), "h"((uint16_t)3) : "memory");
}
__device__ __forceinline__ void prefetch_map(const CUtensorMap* m) {
  asm volatile("prefetch.tensormap [%0];" ::"l"(m) : "memory");
}
__device__ __forceinline__ void fence_async() { asm volatile("fence.proxy.async.global;" ::: "memory"); }
__device__ __forceinline__ void fence_async_smem() { asm volatile("fence.proxy.async.shared::cta;" ::: "memory"); }
__device__ __forceinline__ void bar_sync(int id, int n) { asm volatile("bar.sync %0, %1;" ::"r"(id), "r"(n) : "memory"); }
__device__ __forceinline__ void bar_arrive(int id, int n) { asm volatile("bar.arrive %0, %1;" ::"r"(id), "r"(n) : "memory"); }
__device__ __forceinline__ void wg_fence() { asm volatile("wgmma.fence.sync.aligned;" ::: "memory"); }
__device__ __forceinline__ void wg_commit() { asm volatile("wgmma.commit_group.sync.aligned;" ::: "memory"); }
template <int N> __device__ __forceinline__ void wg_wait() { asm volatile("wgmma.wait_group.sync.aligned %0;" ::"n"(N) : "memory"); }
__device__ __forceinline__ uint64_t make_desc(uint32_t addr, uint32_t lbo, uint32_t sbo) {
  return (uint64_t)((addr & 0x3FFFF) >> 4) | ((uint64_t)(lbo >> 4) << 16) | ((uint64_t)(sbo >> 4) << 32) | (1ull << 62);
}
__device__ __forceinline__ uint32_t ld_relaxed(const uint32_t* p) {
  uint32_t v; asm volatile("ld.relaxed.gpu.global.u32 %0, [%1];" : "=r"(v) : "l"(p) : "memory"); return v;
}
__device__ __forceinline__ uint32_t ld_acquire(const uint32_t* p) {
  uint32_t v; asm volatile("ld.acquire.gpu.global.u32 %0, [%1];" : "=r"(v) : "l"(p) : "memory"); return v;
}
__device__ __forceinline__ uint4 ld_relaxed4(const uint32_t* p) {
  uint4 v; asm volatile("ld.relaxed.gpu.global.v4.u32 {%0,%1,%2,%3}, [%4];" : "=r"(v.x), "=r"(v.y), "=r"(v.z), "=r"(v.w) : "l"(p) : "memory"); return v;
}
__device__ __forceinline__ void st_relaxed(uint32_t* p, uint32_t v) {
  asm volatile("st.relaxed.gpu.global.u32 [%0], %1;" ::"l"(p), "r"(v) : "memory");
}
__device__ __forceinline__ void st_relaxed4(uint32_t* p, uint32_t a, uint32_t b, uint32_t c, uint32_t d) {
  asm volatile("st.relaxed.gpu.global.v4.u32 [%0], {%1,%2,%3,%4};" ::"l"(p), "r"(a), "r"(b), "r"(c), "r"(d) : "memory");
}
__device__ __forceinline__ void st_b128(uint32_t* p, uint32_t a, uint32_t b, uint32_t c, uint32_t d) {
  asm volatile("{ .reg .b64 u, v; .reg .b128 w; mov.b64 u, {%1, %2}; mov.b64 v, {%3, %4}; mov.b128 w, {u, v}; st.relaxed.gpu.global.b128 [%0], w; }"
               ::"l"(p), "r"(a), "r"(b), "r"(c), "r"(d) : "memory");
}
__device__ __forceinline__ uint4 ld_b128(const uint32_t* p) {
  uint4 r;
  asm volatile("{ .reg .b64 u, v; .reg .b128 w; ld.relaxed.gpu.global.b128 w, [%4]; mov.b128 {u, v}, w; mov.b64 {%0, %1}, u; mov.b64 {%2, %3}, v; }"
               : "=r"(r.x), "=r"(r.y), "=r"(r.z), "=r"(r.w) : "l"(p) : "memory");
  return r;
}
__device__ __forceinline__ void st_pairs(uint32_t* p, uint32_t a, uint32_t b, uint32_t tag) {
  asm volatile("{ .reg .b64 u, v; mov.b64 u, {%1, %3}; mov.b64 v, {%2, %3}; st.relaxed.gpu.global.v2.b64 [%0], {u, v}; }"
               ::"l"(p), "r"(a), "r"(b), "r"(tag) : "memory");
}
__device__ __forceinline__ uint4 ld_pairs(const uint32_t* p) {
  uint4 v;
  asm volatile("{ .reg .b64 u, v; ld.relaxed.gpu.global.v2.b64 {u, v}, [%4]; mov.b64 {%0, %1}, u; mov.b64 {%2, %3}, v; }"
               : "=r"(v.x), "=r"(v.y), "=r"(v.z), "=r"(v.w) : "l"(p) : "memory");
  return v;
}
__device__ __forceinline__ uint2 ld_pair(const uint32_t* p) {
  uint2 v;
  asm volatile("{ .reg .b64 u; ld.relaxed.gpu.global.b64 u, [%2]; mov.b64 {%0, %1}, u; }" : "=r"(v.x), "=r"(v.y) : "l"(p) : "memory");
  return v;
}
__device__ __forceinline__ void red_release(uint32_t* p, uint32_t v) {
  asm volatile("red.release.gpu.global.add.u32 [%0], %1;" ::"l"(p), "r"(v) : "memory");
}
__device__ __forceinline__ uint32_t ldg_nc1(const void* p) {
  uint32_t v;
  asm volatile("ld.global.nc.u32 %0, [%1];" : "=r"(v) : "l"(p));
  return v;
}
__device__ __forceinline__ uint4 ldg_nc4(const void* p) {
  uint4 v; asm volatile("ld.global.nc.L1::no_allocate.v4.u32 {%0,%1,%2,%3}, [%4];" : "=r"(v.x), "=r"(v.y), "=r"(v.z), "=r"(v.w) : "l"(p)); return v;
}
__device__ __forceinline__ uint4 ldg_stream4(const void* p) {
  uint4 v;
  asm volatile("ld.global.nc.L1::no_allocate.L2::cache_hint.v4.u32 {%0,%1,%2,%3}, [%4], %5;" : "=r"(v.x), "=r"(v.y), "=r"(v.z), "=r"(v.w) : "l"(p), "l"(l2_stream()));
  return v;
}
__device__ __forceinline__ void stg4(void* p, uint4 v) {
  asm volatile("st.global.v4.u32 [%0], {%1,%2,%3,%4};" ::"l"(p), "r"(v.x), "r"(v.y), "r"(v.z), "r"(v.w) : "memory");
}
__device__ __forceinline__ void wait_counter(const uint32_t* p, uint32_t target) {
  uint32_t n = 0;
  while (__any_sync(0xffffffffu, (int)(ld_acquire(p) - target) < 0)) { watchdog(n); }
}
__device__ __forceinline__ uint32_t tagf(float v, uint32_t tag) { return (__float_as_uint(v) & ~3u) | tag; }
__device__ __forceinline__ bool tag_ok(uint4 v, uint32_t tag) { return (((v.x ^ tag) | (v.y ^ tag) | (v.z ^ tag) | (v.w ^ tag)) & 3u) == 0; }
__device__ __forceinline__ float untag_sum(uint32_t a, uint32_t b) { return __uint_as_float(a & ~3u) + __uint_as_float(b & ~3u); }
__device__ __forceinline__ uint4 poll4(const uint32_t* p, uint32_t tag) {
  uint4 v = ld_relaxed4(p);
  uint32_t n = 0;
  while (!__all_sync(0xffffffffu, tag_ok(v, tag))) { v = ld_relaxed4(p); watchdog(n); }
  return v;
}
__device__ __forceinline__ float bf_lo(uint32_t v) { return __uint_as_float(v << 16); }
__device__ __forceinline__ float bf_hi(uint32_t v) { return __uint_as_float(v & 0xffff0000u); }
__device__ __forceinline__ uint32_t pack_bf(float lo, float hi) {
  uint32_t r; asm("cvt.rn.bf16x2.f32 %0, %1, %2;" : "=r"(r) : "f"(hi), "f"(lo)); return r;
}
__device__ __forceinline__ float rbf(float v) { return __uint_as_float(pack_bf(0.f, v) & 0xffff0000u); }
__device__ __forceinline__ uint32_t hmul2(uint32_t a, uint32_t b) {
  uint32_t r; asm("mul.rn.bf16x2 %0, %1, %2;" : "=r"(r) : "r"(a), "r"(b)); return r;
}
__device__ __forceinline__ uint32_t hadd2(uint32_t a, uint32_t b) {
  uint32_t r; asm("add.rn.bf16x2 %0, %1, %2;" : "=r"(r) : "r"(a), "r"(b)); return r;
}
__device__ __forceinline__ uint32_t hsub2(uint32_t a, uint32_t b) {
  uint32_t r; asm("sub.rn.bf16x2 %0, %1, %2;" : "=r"(r) : "r"(a), "r"(b)); return r;
}
__device__ __forceinline__ float rcp(float x) { float r; asm("rcp.approx.ftz.f32 %0, %1;" : "=f"(r) : "f"(x)); return r; }
__device__ __forceinline__ float ex2(float x) { float r; asm("ex2.approx.ftz.f32 %0, %1;" : "=f"(r) : "f"(x)); return r; }
__device__ __forceinline__ void stmatrix4(uint32_t addr, uint32_t a, uint32_t b, uint32_t c, uint32_t d) {
  asm volatile("stmatrix.sync.aligned.m8n8.x4.shared.b16 [%0], {%1,%2,%3,%4};" ::"r"(addr), "r"(a), "r"(b), "r"(c), "r"(d) : "memory");
}
__device__ __forceinline__ void ldmatrix4(uint32_t addr, uint32_t& a, uint32_t& b, uint32_t& c, uint32_t& d) {
  asm volatile("ldmatrix.sync.aligned.m8n8.x4.shared.b16 {%0,%1,%2,%3}, [%4];" : "=r"(a), "=r"(b), "=r"(c), "=r"(d) : "r"(addr) : "memory");
}
__device__ __forceinline__ void ldmatrix4t(uint32_t addr, uint32_t& a, uint32_t& b, uint32_t& c, uint32_t& d) {
  asm volatile("ldmatrix.sync.aligned.m8n8.x4.trans.shared.b16 {%0,%1,%2,%3}, [%4];" : "=r"(a), "=r"(b), "=r"(c), "=r"(d) : "r"(addr) : "memory");
}
__device__ __forceinline__ void mma16816(float (&d)[4], uint32_t a0, uint32_t a1, uint32_t a2, uint32_t a3, uint32_t b0, uint32_t b1) {
  asm volatile("mma.sync.aligned.m16n8k16.row.col.f32.bf16.bf16.f32 {%0,%1,%2,%3}, {%4,%5,%6,%7}, {%8,%9}, {%0,%1,%2,%3};"
               : "+f"(d[0]), "+f"(d[1]), "+f"(d[2]), "+f"(d[3]) : "r"(a0), "r"(a1), "r"(a2), "r"(a3), "r"(b0), "r"(b1));
}
__device__ __forceinline__ void sts1(uint32_t a, uint32_t v) { asm volatile("st.shared.u32 [%0], %1;" ::"r"(a), "r"(v) : "memory"); }
__device__ __forceinline__ uint4 lds4(uint32_t a) {
  uint4 v; asm volatile("ld.shared.v4.u32 {%0,%1,%2,%3}, [%4];" : "=r"(v.x), "=r"(v.y), "=r"(v.z), "=r"(v.w) : "r"(a) : "memory"); return v;
}
__device__ __forceinline__ uint2 lds2(uint32_t a) {
  uint2 v; asm volatile("ld.shared.v2.u32 {%0,%1}, [%2];" : "=r"(v.x), "=r"(v.y) : "r"(a) : "memory"); return v;
}
__device__ __forceinline__ uint32_t lds1(uint32_t a) {
  uint32_t v; asm volatile("ld.shared.u32 %0, [%1];" : "=r"(v) : "r"(a) : "memory"); return v;
}
__device__ __forceinline__ void sts2(uint32_t a, uint32_t x, uint32_t y) { asm volatile("st.shared.v2.u32 [%0], {%1,%2};" ::"r"(a), "r"(x), "r"(y) : "memory"); }
__device__ __forceinline__ void sts4(uint32_t a, uint4 v) {
  asm volatile("st.shared.v4.u32 [%0], {%1,%2,%3,%4};" ::"r"(a), "r"(v.x), "r"(v.y), "r"(v.z), "r"(v.w) : "memory");
}
__device__ __forceinline__ float silu_f(float v) { return __fdividef(v, 1.f + __expf(-v)); }
__device__ __forceinline__ uint32_t hfma2(uint32_t a, uint32_t b, uint32_t c) {
  uint32_t r; asm("fma.rn.bf16x2 %0, %1, %2, %3;" : "=r"(r) : "r"(a), "r"(b), "r"(c)); return r;
}
__device__ __forceinline__ void split_inv(float sd, uint32_t& ih, uint32_t& il) {
  const float inv = rcp(sd);
  ih = pack_bf(inv, inv);
  const float lo = inv - bf_lo(ih);
  il = pack_bf(lo, lo);
}
__device__ __forceinline__ uint32_t ln_norm(uint32_t x, uint32_t mean2, uint32_t ih, uint32_t il) {
  const uint32_t d = hsub2(x, mean2);
  return hfma2(d, ih, hmul2(d, il));
}
__device__ __forceinline__ uint32_t ln_mod(uint32_t x, uint32_t mean2, uint32_t ih, uint32_t il, uint32_t c1, uint32_t sh) {
  return hadd2(hmul2(ln_norm(x, mean2, ih, il), c1), sh);
}

#define R8(a, i) "+f"(a[i]), "+f"(a[i + 1]), "+f"(a[i + 2]), "+f"(a[i + 3]), "+f"(a[i + 4]), "+f"(a[i + 5]), "+f"(a[i + 6]), "+f"(a[i + 7])
#define D64 "{%0,%1,%2,%3,%4,%5,%6,%7,%8,%9,%10,%11,%12,%13,%14,%15,%16,%17,%18,%19,%20,%21,%22,%23,%24,%25,%26,%27,%28,%29,%30,%31," \
            "%32,%33,%34,%35,%36,%37,%38,%39,%40,%41,%42,%43,%44,%45,%46,%47,%48,%49,%50,%51,%52,%53,%54,%55,%56,%57,%58,%59,%60,%61,%62,%63}"
template <int TB>
__device__ __forceinline__ void mma_ss(float (&d)[64], uint64_t da, uint64_t db, int sc) {
  asm volatile("{\n.reg .pred p;\nsetp.ne.b32 p, %66, 0;\n"
               "wgmma.mma_async.sync.aligned.m64n128k16.f32.bf16.bf16 " D64 ", %64, %65, p, 1, 1, 0, %67;\n}"
               : R8(d, 0), R8(d, 8), R8(d, 16), R8(d, 24), R8(d, 32), R8(d, 40), R8(d, 48), R8(d, 56)
               : "l"(da), "l"(db), "r"(sc), "n"(TB));
}
template <int TB>
__device__ __forceinline__ void mma_rs(float (&d)[64], uint32_t a0, uint32_t a1, uint32_t a2, uint32_t a3, uint64_t db, int sc) {
  asm volatile("{\n.reg .pred p;\nsetp.ne.b32 p, %69, 0;\n"
               "wgmma.mma_async.sync.aligned.m64n128k16.f32.bf16.bf16 " D64 ", {%64,%65,%66,%67}, %68, p, 1, 1, %70;\n}"
               : R8(d, 0), R8(d, 8), R8(d, 16), R8(d, 24), R8(d, 32), R8(d, 40), R8(d, 48), R8(d, 56)
               : "r"(a0), "r"(a1), "r"(a2), "r"(a3), "l"(db), "r"(sc), "n"(TB));
}
#define D128 "{%0,%1,%2,%3,%4,%5,%6,%7,%8,%9,%10,%11,%12,%13,%14,%15,%16,%17,%18,%19,%20,%21,%22,%23,%24,%25,%26,%27,%28,%29,%30,%31," \
             "%32,%33,%34,%35,%36,%37,%38,%39,%40,%41,%42,%43,%44,%45,%46,%47,%48,%49,%50,%51,%52,%53,%54,%55,%56,%57,%58,%59,%60,%61,%62,%63," \
             "%64,%65,%66,%67,%68,%69,%70,%71,%72,%73,%74,%75,%76,%77,%78,%79,%80,%81,%82,%83,%84,%85,%86,%87,%88,%89,%90,%91,%92,%93,%94,%95," \
             "%96,%97,%98,%99,%100,%101,%102,%103,%104,%105,%106,%107,%108,%109,%110,%111,%112,%113,%114,%115,%116,%117,%118,%119,%120,%121,%122,%123,%124,%125,%126,%127}"
#define R128(d, e) R8(d, 0), R8(d, 8), R8(d, 16), R8(d, 24), R8(d, 32), R8(d, 40), R8(d, 48), R8(d, 56), \
                   R8(e, 0), R8(e, 8), R8(e, 16), R8(e, 24), R8(e, 32), R8(e, 40), R8(e, 48), R8(e, 56)
__device__ __forceinline__ void mma256_ss(float (&d)[64], float (&e)[64], uint64_t da, uint64_t db, int sc) {
  asm volatile("{\n.reg .pred p;\nsetp.ne.b32 p, %130, 0;\n"
               "wgmma.mma_async.sync.aligned.m64n256k16.f32.bf16.bf16 " D128 ", %128, %129, p, 1, 1, 0, 1;\n}"
               : R128(d, e) : "l"(da), "l"(db), "r"(sc));
}
__device__ __forceinline__ void mma256_rs(float (&d)[64], float (&e)[64], uint32_t a0, uint32_t a1, uint32_t a2, uint32_t a3, uint64_t db) {
  asm volatile("{\n.reg .pred p;\nsetp.ne.b32 p, 1, 0;\n"
               "wgmma.mma_async.sync.aligned.m64n256k16.f32.bf16.bf16 " D128 ", {%128,%129,%130,%131}, %132, p, 1, 1, 1;\n}"
               : R128(d, e) : "r"(a0), "r"(a1), "r"(a2), "r"(a3), "l"(db));
}
template <int N> __device__ __forceinline__ void keep(float (&a)[N]) {
#pragma unroll
  for (int i = 0; i < N; i++) asm volatile("" : "+f"(a[i])::"memory");
}
template <int N> __device__ __forceinline__ void keep(uint32_t (&a)[N]) {
#pragma unroll
  for (int i = 0; i < N; i++) asm volatile("" : "+r"(a[i])::"memory");
}

#define STAMP(idx) do {} while (0)
#define PROF(grp, cond, idx) do {} while (0)

constexpr float SCL2 = 1.4426950408889634f * 0.08838834764831845f;

__device__ __forceinline__ void pack_p(const float (&s)[64], uint32_t (&p)[32]) {
#pragma unroll
  for (int i = 0; i < 32; i++) p[i] = pack_bf(s[2 * i], s[2 * i + 1]);
}

__device__ __forceinline__ void issue_qk(float (&s)[64], uint32_t q0, uint32_t q1, uint32_t kslot) {
  const uint64_t db = make_desc(kslot, 16, 1024), da0 = make_desc(q0, 16, 1024), da1 = make_desc(q1, 16, 1024);
#pragma unroll
  for (int kk = 0; kk < 8; kk++) mma_ss<0>(s, (kk < 4 ? da0 : da1) + (kk & 3) * 2, db + (kk >> 2) * 1024 + (kk & 3) * 2, kk != 0);
}
__device__ __forceinline__ void issue_pv(float (&o)[64], uint32_t (&p)[32], uint32_t vslot, int acc) {
  uint64_t db = make_desc(vslot, 16384, 1024);
#pragma unroll
  for (int kk = 0; kk < 8; kk++)
    mma_rs<1>(o, p[4 * kk], p[4 * kk + 1], p[4 * kk + 2], p[4 * kk + 3], db + kk * 128, kk == 0 ? acc : 1);
}

template <int H>
__device__ __forceinline__ void store_chunk(const float (&a)[64], uint32_t addr) {
#pragma unroll
  for (int i = 8 * H; i < 8 * H + 8; i += 2)
    stmatrix4(addr ^ ((i & 7) << 4), pack_bf(a[4 * i], a[4 * i + 1]), pack_bf(a[4 * i + 2], a[4 * i + 3]),
              pack_bf(a[4 * i + 4], a[4 * i + 5]), pack_bf(a[4 * i + 6], a[4 * i + 7]));
}
template <int H>
__device__ __forceinline__ void store_chunk(const float (&a)[64], float i0, float i1, uint32_t addr) {
#pragma unroll
  for (int i = 8 * H; i < 8 * H + 8; i += 2)
    stmatrix4(addr ^ ((i & 7) << 4), pack_bf(a[4 * i] * i0, a[4 * i + 1] * i0), pack_bf(a[4 * i + 2] * i1, a[4 * i + 3] * i1),
              pack_bf(a[4 * i + 4] * i0, a[4 * i + 5] * i0), pack_bf(a[4 * i + 6] * i1, a[4 * i + 7] * i1));
}
__device__ __forceinline__ float inv_quad_sum(float l) {
  l += __shfl_xor_sync(0xffffffffu, l, 1);
  l += __shfl_xor_sync(0xffffffffu, l, 2);
  return rcp(l);
}

__device__ __forceinline__ void write_table(uint32_t table, bool ca, uint32_t t, const uint4& m0, const uint4& m1) {
  float c0 = untag_sum(m0.x, m1.x), c1 = untag_sum(m0.y, m1.y), c2 = untag_sum(m0.z, m1.z), c3 = untag_sum(m0.w, m1.w);
  if (ca) { c0 = 1.f + rbf(c0); c1 = 1.f + rbf(c1); c2 = 1.f + rbf(c2); c3 = 1.f + rbf(c3); }
  const uint32_t d = table + (t >> 2) * 64 + (t & 1) * 32 + (t & 2) * 2 + (ca ? 0 : 8);
  sts1(d, pack_bf(c0, c1));
  sts1(d + 16, pack_bf(c2, c3));
}

__device__ __forceinline__ void ln_scalars(float mean, float var, float& mb, float& sd) {
  mb = rbf(mean);
  float r; asm("sqrt.approx.ftz.f32 %0, %1;" : "=f"(r) : "f"(rbf(rbf(var) + 1e-5f)));
  sd = rbf(r);
}

__global__ void __cluster_dims__(2, 1, 1) __launch_bounds__(384, 1) fused_kernel(const __grid_constant__ Maps maps, const Ptrs P) {
  extern __shared__ __align__(1024) uint8_t smem_raw[];
  const uint32_t base = smem_u32(smem_raw);
  const int tid = threadIdx.x, lane = tid & 31;
  const int warp = __shfl_sync(0xffffffffu, tid >> 5, 0);
  const int b = blockIdx.x;
  PROF(31, tid == 0, 0);

  if (b >= NMAIN) {
    float* sc = reinterpret_cast<float*>(smem_raw);
    float* red = sc + DM;
    for (int k = tid; k < DM; k += 384) sc[k] = rbf(silu_f(__bfloat162float(P.c[k])));
    __syncthreads();
    if (tid < 256) {
      const int col = 2048 + (b - NMAIN) * 1024 + (tid & 127) * 8, r0 = (tid >> 7) * 512;
      float acc[8];
#pragma unroll
      for (int e = 0; e < 8; e++) acc[e] = 0.f;
#pragma unroll 1
      for (int r = r0; r < r0 + 512; r += HU) {
        uint4 w[HU];
#pragma unroll
        for (int u = 0; u < HU; u++) w[u] = ldg_stream4(P.w_mod + (size_t)(r + u) * NMOD + col);
#pragma unroll
        for (int u = 0; u < HU; u++) {
          float s = sc[r + u];
          acc[0] += s * bf_lo(w[u].x); acc[1] += s * bf_hi(w[u].x); acc[2] += s * bf_lo(w[u].y); acc[3] += s * bf_hi(w[u].y);
          acc[4] += s * bf_lo(w[u].z); acc[5] += s * bf_hi(w[u].z); acc[6] += s * bf_lo(w[u].w); acc[7] += s * bf_hi(w[u].w);
        }
      }
      if (tid >= 128) {
#pragma unroll
        for (int e = 0; e < 8; e++) red[(tid & 127) * 8 + e] = acc[e];
      }
      const uint32_t tag = ld_relaxed(&g_epoch) % 3 + 1;
      bar_sync(1, 256);
      if (tid < 128) {
        uint32_t o[8];
#pragma unroll
        for (int e = 0; e < 8; e++) o[e] = __float_as_uint(rbf(acc[e] + red[tid * 8 + e])) | tag;
        st_relaxed4(g_mod + col, o[0], o[1], o[2], o[3]);
        st_relaxed4(g_mod + col + 4, o[4], o[5], o[6], o[7]);
        const uint4 wr = ldg_nc4(P.w_r + tid * 8);
        const uint32_t wv[4] = {wr.x, wr.y, wr.z, wr.w};
        float dsum = 0.f;
#pragma unroll
        for (int e = 0; e < 8; e++) {
          const float m = bf_hi(o[e]);
          dsum += (b == NMAIN + 2 ? rbf(1.f + m) : m) * ((e & 1) ? bf_hi(wv[e >> 1]) : bf_lo(wv[e >> 1]));
        }
#pragma unroll
        for (int k = 16; k > 0; k >>= 1) dsum += __shfl_xor_sync(0xffffffffu, dsum, k);
        if (lane == 0) st_relaxed(g_mod + (b - NMAIN) * 4 + warp, tagf(dsum, tag));
      }
    }
    PROF(2, tid == 0, 1);
    return;
  }

  const int rank = b & 1;
  const int rb = ((b >> 4) << 1) | rank, cj = (b >> 1) & 7;
  const bool late = b & 4;
  const uint32_t bfull = base + OFF_BAR, bempty = bfull + NSLOT * 8;
  const uint32_t gfull = bempty + NSLOT * 8, gempty = gfull + 32;
  const uint32_t bar_ofull = gempty + 32;
  const uint32_t bar_ofree = bar_ofull + 32;
  const uint32_t bar_par = bar_ofree + 32;
  const uint32_t bar_mod = bar_par + 8;
  const uint32_t bar_pread = bar_mod + 8;
  const uint32_t bar_xres = bar_pread + 8;
  const uint32_t bar_ring = bar_xres + 8;
  const uint32_t bar_box = bar_ring + 24;
  const uint32_t bar_go = bar_box + 96;
  const uint32_t bar_go2 = bar_go + 16;
  const uint32_t bar_cnt = bar_go + 24;
  const uint32_t xfull = bar_go + 40, xempty = xfull + 32;
  const uint32_t bar_hw = xempty + 32, bar_hx = bar_hw + 8;
  const uint32_t bar_hpub = bar_hx + 16;
  const uint32_t bar_win = bar_hpub + 16;
  const uint32_t bar_rx = bar_win + 8;
  const uint32_t bar_sel = bar_rx + 8;
  const uint32_t bar_gate = bar_sel + 8;
  const uint32_t bar_rel = bar_gate + 8;
  const uint32_t bar_od = bar_rel + 8;
  const uint32_t bar_mod2 = bar_od + 8;
  const uint32_t bar_res = bar_go + 8;
  const uint32_t stage = base + OFF_STAGE, par = base + OFF_PAR;

  if (warp == 10 && elect_one()) prefetch_map(&maps.wm);
  if (warp == 8 && elect_one()) {
    for (int s = 0; s < NSLOT; s++) { mbar_init(bfull + s * 8, 1); mbar_init(bempty + s * 8, 16); }
    for (int s = 0; s < 4; s++) { mbar_init(gfull + s * 8, 1); mbar_init(gempty + s * 8, 16); mbar_init(xfull + s * 8, 1); mbar_init(xempty + s * 8, 8); mbar_init(bar_ofree + s * 8, 1); mbar_init(bar_ofull + s * 8, 128); }
    mbar_init(bar_par, 64); mbar_init(bar_mod, 256); mbar_init(bar_pread, 2); mbar_init(bar_xres, 1);
    mbar_init(bar_ring, 8); mbar_init(bar_ring + 8, 8); mbar_init(bar_ring + 16, 8);
    mbar_init(bar_go, 1); mbar_init(bar_go2, 1); mbar_init(bar_cnt, 1); mbar_init(bar_cnt + 8, 1); mbar_init(bar_hpub, 8); mbar_init(bar_hpub + 8, 8); mbar_init(bar_res, 1); mbar_init(bar_win, 1); mbar_init(bar_rx, 1); mbar_init(bar_sel, 64); mbar_init(bar_gate, 8); mbar_init(bar_rel, 8); mbar_init(bar_od, 1); mbar_init(bar_mod2, 64);
    for (int s = 0; s < 12; s++) mbar_init(bar_box + s * 8, 1);
    asm volatile("fence.mbarrier_init.release.cluster;" ::: "memory");
    prefetch_map(&maps.x); prefetch_map(&maps.wq); prefetch_map(&maps.k); prefetch_map(&maps.v);
  }
  if (warp == 9 && elect_one()) {
    mbar_init(bar_hw, 1); mbar_init(bar_hx, 1); mbar_init(bar_hx + 8, 1);
    asm volatile("fence.mbarrier_init.release.cluster;" ::: "memory");
    mbar_expect_tx(bar_hw, 32768);
    mbar_expect_tx(bar_hx, 16384);
    mbar_expect_tx(bar_hx + 8, 16384);
    const __nv_bfloat16* xs = P.x + (size_t)(rb * 128 + cj * 16) * DM;
    bulk_load(base + 2 * GST_BYTES, xs, 16384, bar_hx);
    if (!late) {
      tma2d(stage, &maps.wm, (b >> 1) * 32, rank * 512, bar_hw);
      tma2d(stage + 16384, &maps.wm, (b >> 1) * 32, rank * 512 + 256, bar_hw);
    }
    bulk_load(base + 3 * GST_BYTES, xs + 8 * DM, 16384, bar_hx + 8);
  }
  cluster_arrive();

  if (warp >= 8) {
    asm volatile("setmaxnreg.dec.sync.aligned.u32 40;");
    if (warp < 10) bar_arrive(1, 320);
    const uint32_t epoch = ld_relaxed(&g_epoch);
    cluster_wait();
    if (warp == 8) {
      const int kvrow = (cj >> 1) * SK + (SK - WIN);
      int wch = cj * 8 + rank * 2;
#pragma unroll 1
      for (int ps = 0; ps < 3; ps++) {
        const CUtensorMap* mw = ps == 2 ? &maps.wo : &maps.wq;
        const uint32_t xt = ps == 1 ? XT1 : XT2, wt = ps == 0 ? WT0 : (ps == 1 ? WT1 : WT2);
        const int nst = ps == 2 ? 32 : 16;
#pragma unroll 1
        for (int i = 0; i < nst; i++) {
          const uint32_t bf = gfull + (i & 3) * 8;
          const int kt = ps == 2 ? (((cj & 1) * 4 + ((i >> 1) & 3)) * 4 + (i >> 3)) * 2 + (i & 1) : (ps ? i : slice_of(i) + (b & 14)) & 15;
          const uint32_t wd = base + unit_of(wt, i & 3) + rank * UNIT, xd = base + unit_of(xt, i & 3);
          const uint8_t* xs = g_act + (uint32_t)(rb * 80 + (ps - 1) * 16 + kt) * UNIT;
          if (ps == 0 && i == HD) mbar_wait(bar_mod, 0);
          if (ps == 2 && (i & 7) == 0 && i != 8) mbar_wait(i ? bar_cnt + i - 16 : bar_ofree + 24, 0);
          if ((i & 7) == 0) fence_async();
          if (i == RES0) mbar_wait(bar_res, 0);
          mbar_wait(bf, ((i >> 2) & 1) ^ 1);
          if (elect_one()) {
            mbar_expect_tx(bf, ps ? GST_BYTES : 2 * UNIT);
            if (ps && i < 2) bulk_load_stream(xd, xs, UNIT, bf);
            mbar_arrive_pred(bar_go, i == GOST);
            mbar_arrive_pred(bar_go2, ps == 1 && i == PG0);
            mbar_arrive_pred(bar_od, ps && i == (ps == 1 ? ODS1 : ODS) + 1);
            if (i == RES0) mbar_expect_tx(bar_xres, 32768);
          }
          const int wk = (i == 31 ? kt ^ (rank * 32) : kt) * 64, wc = i == 31 ? cj * 2 : wch;
          const uint64_t xp = i == 31 ? l2_normal() : l2_stream();
          mbar_wait(ps && i < 4 ? bempty + i * 8 : gempty + (i & 3) * 8, ((i >> 2) & 1) ^ 1);
          if (elect_one()) {
            tma3d_mc<true>(wd, mw, 0, wk, wc, bf);
            if (ps && i > 2) bulk_load_stream(xd, xs, UNIT, bf, xp);
            if (i == RES0 || i == RES1) tma2d(base + OFF_RES + (i == RES1) * UNIT, &maps.x, cj * 128 + (i == RES1) * 64, rb * 128, bar_xres);
          }
          if (ps && i == 2) {
            mbar_wait(bar_ofree + (ps - 1) * 16, 0);
            if (elect_one()) bulk_load_stream(xd, xs, UNIT, bf);
          }
        }
        if (ps == 2) break;
        wch = ps ? ((wch >> 3) ^ rank) * 2 : wch + 4;
#pragma unroll 1
        for (int u = 0; u < 16; u++) {
          const bool isk = (u == 0) || ((u & 1) && u < 15);
          const int blk = (isk ? (u + 1) >> 1 : (u == 15 ? 7 : (u >> 1) - 1)) & 3;
          const uint32_t sl = base + unit_of(ps ? AT1 : AT0, u & 3) + rank * UNIT, bf = bfull + (u & 3) * 8;
          mbar_wait(bf, ((u >> 2) & 1) ^ 1);
          if (elect_one()) mbar_expect_tx(bf, SLOT_BYTES);
          mbar_wait(u < 4 ? gempty + ((u + 1) >> 1) * 8 : bempty + (u & 3) * 8, ((u >> 2) & 1) ^ 1);
          if (elect_one()) {
            if (ps && u >= 7 && u != 8) tma3d_mc<true>(sl, isk ? &maps.k : &maps.v, 0, kvrow + blk * 128, rank, bf);
            else tma3d_mc<false>(sl, isk ? &maps.k : &maps.v, 0, kvrow + blk * 128, rank, bf);
          }
        }
      }
      if (elect_one()) mbar_expect_tx(bar_rx, UNIT);
      mbar_wait(bar_rel, 0);
      if (elect_one()) {
        bulk_load_stream(base + UNIT, g_act + (uint32_t)(rb * 80 + 16 + 63 - (cj & 1) * 32) * UNIT, UNIT, bar_rx);
      }
      if (b < NFFN) {
#pragma unroll 1
        for (int u = 0; u < 12; u++) {
          const uint32_t dst = base + unit_of(u < 4 ? FT_G : (u < 8 ? FT_U : FT_D), u & 3);
          if (elect_one()) mbar_expect_tx(bar_box + u * 8, UNIT);
          if (u == 0 || u == 2 || u == 8) mbar_wait(bar_ring + (u == 8 ? 16 : u * 4), 0);
          const int fp = u < 8 ? FPACE0 : FPACE;
          if (u >= fp) mbar_wait(bar_box + (u - fp) * 8, 0);
          if (elect_one()) {
            if (u < 8) tma2d(dst, u < 4 ? &maps.wg : &maps.wu, b * 32, (u & 3) * 256, bar_box + u * 8);
            else tma3d(dst, &maps.wd, 0, b * 32, (u - 8) * 4, bar_box + u * 8);
          }
        }
      }
    } else if (warp == 9) {
      const uint32_t target = 8 * (epoch + 1);
      uint32_t hmask = 0;
#pragma unroll 1
      for (int i = 0; i < 16; i++) {
        if (i == HDX) mbar_wait(bar_mod, 0);
        const int kt = (2 * cj + slice_of(i)) & 15;
        const uint32_t need = i == 15 ? 0xffffu : 1u << kt;
        if (i >= NRS && (hmask & need) != need) {
          uint32_t n = 0;
          do { hmask = __ballot_sync(0xffffffffu, ld_acquire(&g_cnt_h[rb * 32 + (lane & 15)]) == epoch + 1); watchdog(n); } while ((hmask & need) != need);
          PROF(1, lane == 0 && i == NRS, 26);
          fence_async();
        }
        mbar_wait(xempty + (i & 3) * 8, ((i >> 2) & 1) ^ 1);
        if (elect_one()) {
          mbar_expect_tx(xfull + (i & 3) * 8, UNIT);
          if (i < NRS) tma2d(base + (i & 3) * GST_BYTES, &maps.x, kt * 64, rb * 128, xfull + (i & 3) * 8);
          else bulk_load_stream(base + (i & 3) * GST_BYTES, g_act + (uint32_t)(rb * 80 + kt) * UNIT, UNIT, xfull + (i & 3) * 8);
        }
      }
      prefetch_map(&maps.wo);
#pragma unroll 1
      for (int t = 0; t < 4; t++) {
        if (t & 1) mbar_wait(bar_od, t >> 1);
        const int ops = OPS >> (t & 1);
#pragma unroll 1
        for (int p = 0; p < 32768; p += ops) {
          const uint32_t w = p >> 14, c = (p >> 13) & 1, off = w * 8192 + (p & 8191);
          mbar_wait(bar_ofull + (t & 1) * 16 + w * 8, t >> 1);
          if (elect_one()) {
            bulk_store(g_act + (uint32_t)(rb * 80 + 16 + (cj * 4 + t) * 2 + c) * UNIT + off, base + unit_of(QT, 2 * t + c) + off, ops);
            asm volatile("cp.async.bulk.commit_group;" ::: "memory");
            asm volatile("cp.async.bulk.wait_group.read 0;" ::: "memory");
          }
        }
        if (elect_one()) {
          mbar_arrive(t < 3 ? bar_ofree + t * 8 : bar_res);
          asm volatile("cp.async.bulk.wait_group 0;" ::: "memory");
          fence_async();
          red_release(&g_cnt_o[((rb * 4 + t) * 2 + (cj >> 2)) * 32], 2);
        }
        if (t) {
          wait_counter(&g_cnt_o[(rb * 8 + 2 * t + (cj & 1)) * 32], target);
          if (t & 1) wait_counter(&g_cnt_o[(rb * 8 + (t == 1 ? cj & 1 : 7 - (cj & 1))) * 32], target);
          if (elect_one()) mbar_arrive(t == 1 ? bar_ofree + 24 : bar_cnt + t * 8 - 16);
        }
      }
      PROF(2, lane == 0, 27);
      const uint32_t tag = epoch % 3 + 1;
      const uint32_t* inbox = g_cand + (b >> 1) % CR * 512 + (lane & 15) * CS;
      mbar_wait(bar_ring + 16, 0);
      uint32_t c0 = ld_relaxed(inbox), n = 0;
#define CAND_STEP(cv)                                                                                        \
      {                                                                                                      \
        const bool valid = (cv & 3u) == tag, all = __all_sync(0xffffffffu, valid);                           \
        const uint32_t best = __reduce_max_sync(0xffffffffu, valid ? cv : 0u);                               \
        const uint32_t blk = __ffs(__ballot_sync(0xffffffffu, cv == best)) - 1;                              \
        if (best) sts2(par + PAR_CONST + 56, best, (blk << 7 | (~best >> 2 & 127)) | (all ? 0x1800 : 0x800)); \
        if (all) break;                                                                                      \
        cv = ld_relaxed(inbox);                                                                              \
      }
      while (true) { CAND_STEP(c0) watchdog(n); }
    } else {
      const int t2 = tid - 320;
      if (late && warp == 10) {
        mbar_wait(bar_hx, 0);
        if (elect_one()) {
          tma2d(stage, &maps.wm, (b >> 1) * 32, rank * 512, bar_hw);
          tma2d(stage + 16384, &maps.wm, (b >> 1) * 32, rank * 512 + 256, bar_hw);
        }
      }
      {
        const uint32_t tag = epoch % 3 + 1;
        mbar_wait(bar_hx + 8, 0);
        mbar_wait(bar_hw, 0);
        __nanosleep(late ? OSL2 : OSL);
        {
          const uint32_t t7 = (warp & 1) * 64 + (lane >> 4) * 32 + 16 + (lane & 15);
          const uint32_t* pm = g_modp + ((cj * 128 + t7 * 4) & (DM - 1));
          uint4 m0, m1, m2, m3;
          uint32_t n = 0;
          do {
            m0 = ld_relaxed4(pm); m1 = ld_relaxed4(pm + 2 * DM); m2 = ld_relaxed4(pm + DM); m3 = ld_relaxed4(pm + 3 * DM);
            watchdog(n);
          } while (!__all_sync(0xffffffffu, tag_ok(m0, tag) && tag_ok(m1, tag) && tag_ok(m2, tag) && tag_ok(m3, tag)));
          write_table(par, false, t7, m0, m1);
          write_table(par, true, t7, m2, m3);
          mbar_arrive(bar_mod2);
        }
      }
      mbar_wait(bar_hpub + (warp & 1) * 8, 0);
      PROF(1, t2 == 0, 24);
#pragma unroll 1
      for (int c = 0; c < 8; c++) {
        const uint32_t off = (warp & 1) * UNIT + c * 2048 + lane * 16;
        uint8_t* dst = g_act + (uint32_t)(rb * 80 + cj * 2) * UNIT + off;
        const uint4 v0 = lds4(stage + off), v1 = lds4(stage + off + 512), v2 = lds4(stage + off + 1024), v3 = lds4(stage + off + 1536);
        stg4(dst, v0); stg4(dst + 512, v1); stg4(dst + 1024, v2); stg4(dst + 1536, v3);
      }
      __syncwarp();
      PROF(1, t2 == 0, 15);
      if (lane == 0) {
        mbar_arrive(bar_pread);
        red_release(&g_cnt_h[rb * 32 + cj * 2 + (warp & 1)], 1);
        PROF(1, t2 == 0, 25);
        prefetch_map(&maps.wg); prefetch_map(&maps.wu); prefetch_map(&maps.wd); prefetch_map(&maps.out);
      }
      __syncwarp();
      if (b < NFFN) {
        mbar_wait(bar_go2, 0);
        const __nv_bfloat16* pg = ((b & 1) ? P.w_up : P.w_gate) + (b >> 1) * 64 + (size_t)t2 * FF;
        const __nv_bfloat16* pd = P.w_down + (size_t)b * 32768 + t2 * 64;
        PROF(2, t2 == 0, 13);
#pragma unroll 1
        for (int i = 0; i < WN; i += WB) {
          uint32_t v[WB];
#pragma unroll
          for (int u = 0; u < WB; u++) {
            const int k = i + u;
            asm volatile("ld.global.cg.L2::128B.u32 %0, [%1];" : "=r"(v[u]) : "l"(k < 16 ? pg + (size_t)k * 64 * FF : pd + (k - 16) * 4096));
          }
#pragma unroll
          for (int u = 1; u < WB; u++) v[0] ^= v[u];
          sts1(par + PAR_SINK + t2 * 4, v[0]);
        }
        PROF(2, t2 == 0, 14);
      }
      const uint32_t tag = epoch % 3 + 1;
      mbar_wait(bar_go, 0);
      bar_sync(4, 64);
      if (warp == 10) {
        const uint32_t* src = g_mod + 2 * DM + cj * 128 + lane * 4;
        const uint2 wr = *reinterpret_cast<const uint2*>(P.w_r + cj * 128 + lane * 4);
        uint4 vga, vsb, vcb, vgb;
        uint32_t n = 0;
        do {
          vga = ld_relaxed4(src); vsb = ld_relaxed4(src + DM); vcb = ld_relaxed4(src + 2 * DM); vgb = ld_relaxed4(src + 3 * DM);
          watchdog(n);
        } while (!__all_sync(0xffffffffu, tag_ok(vga, tag) && tag_ok(vsb, tag) && tag_ok(vcb, tag) && tag_ok(vgb, tag)));
        const float c0 = rbf(1.f + bf_hi(vcb.x)), c1 = rbf(1.f + bf_hi(vcb.y)), c2 = rbf(1.f + bf_hi(vcb.z)), c3 = rbf(1.f + bf_hi(vcb.w));
        const float a0 = c0 * bf_lo(wr.x), a1 = c1 * bf_hi(wr.x), a2 = c2 * bf_lo(wr.y), a3 = c3 * bf_hi(wr.y);
        const uint32_t h0 = pack_bf(a0, a1), h1 = pack_bf(a2, a3);
        const uint32_t t1 = par + PAR_T1 + (lane >> 2) * 64 + (lane & 1) * 32 + (lane & 2) * 2;
        sts1(t1, h0); sts1(t1 + 8, pack_bf(a0 - bf_lo(h0), a1 - bf_hi(h0)));
        sts1(t1 + 16, h1); sts1(t1 + 24, pack_bf(a2 - bf_lo(h1), a3 - bf_hi(h1)));
        const uint32_t tg = par + PAR_SINK + (lane >> 3) * 64 + (lane & 1) * 32 + (lane & 6) * 2;
        sts1(tg, __byte_perm(vga.x, vga.y, 0x7632)); sts1(tg + 16, __byte_perm(vga.z, vga.w, 0x7632));
        sts4(par + PAR_T2 + lane * 32, make_uint4(pack_bf(c0, c1), __byte_perm(vsb.x, vsb.y, 0x7632), __byte_perm(vgb.x, vgb.y, 0x7632), __byte_perm(vga.x, vga.y, 0x7632)));
        sts4(par + PAR_T2 + lane * 32 + 16, make_uint4(pack_bf(c2, c3), __byte_perm(vsb.z, vsb.w, 0x7632), __byte_perm(vgb.z, vgb.w, 0x7632), __byte_perm(vga.z, vga.w, 0x7632)));
      } else {
        const uint4 g = poll4((lane & 8) ? g_mod + 8 - (lane & 1) * 4 : g_mod + 5 * DM + (b >> 4) * 128 + (lane & 7) * 16 + (b & 12), tag);
        sts1(par + PAR_CONST + 60, 0);
        if (lane < 8) sts1(par + PAR_CONST + 16 + lane * 4, (b & 2) ? ((b & 1) ? g.w : g.z) : ((b & 1) ? g.y : g.x));
        else if (lane < 10) sts2(par + PAR_CONST + (lane - 8) * 8, __float_as_uint(untag_sum(g.x, g.y) + untag_sum(g.z, g.w)), epoch);
      }
      __syncwarp();
#pragma unroll 1
      for (int q = 0; q < 32; q++) {
        st_b128(g_xch + ((size_t)b * 8 * 256 + q * 64 + t2) * 4, (epoch & 1) << 16, 0, 0, 0);
        __nanosleep(RSL);
      }
      for (int q = 0; q < 2; q++) st_relaxed4(g_stats + (((rb * 8 + q * 4 + (t2 >> 4)) * 8 + cj) * 16 + (t2 & 15)) * 4, 0, 0, 0, 0);
      if (b < NFFN)
        for (int q = 0; q < 2; q++) st_relaxed4(ypart_slot(b, q * 64 + t2), 0, 0, 0, 0);
      st_relaxed4(g_row + rb * 2 * DM + (t2 >> 5) * DM + cj * 128 + (t2 & 31) * 4, 0, 0, 0, 0);
      __threadfence();
      mbar_arrive(bar_par);
      mbar_wait(bar_gate, 0);
      uint32_t have = 0, n = 0;
      while (true) {
        const uint32_t st = lds1(par + PAR_CONST + 60) >> 7;
        if ((st & 31) != have) {
          const uint32_t* hsrc = g_row + (st & 15) * 2 * DM + t2 * 4;
          uint4 hv[4];
          bool ok = true;
#pragma unroll
          for (int i = 0; i < 4; i++) hv[i] = ld_pairs(hsrc + i * 256);
#pragma unroll
          for (int i = 0; i < 4; i++) {
            sts2(base + ((FT_G >> i * 4) & 15) * UNIT + (warp & 1) * 8192 + 256 + lane * 8, hv[i].x, hv[i].z);
            ok = ok && hv[i].y == tag && hv[i].w == tag;
          }
          have = __all_sync(0xffffffffu, ok) ? st & 31 : 0;
        }
        if ((st ^ have) == 32) break;
        watchdog(n);
      }
      mbar_arrive(bar_sel);
    }
    __syncwarp();
    cluster_arrive();
    {
      const uint32_t tag = epoch % 3 + 1, t3 = tid - 256;
      mbar_wait(bar_win, 0);
      uint2 win = lds2(par + PAR_CONST + 56);
      win.y &= 0x7ff;
      const uint32_t* fsrc = g_row + (win.y >> 7) * 2 * DM + (b >> 4) * 128 + (t3 & 7) * 16 + (b & 6) * 2 + ((b >> 2) & 2);
      const uint32_t* ysrc = ypart_slot(min(t3, NFFN - 1), b);
      uint2 fh = ld_pair(fsrc), fx = ld_pair(fsrc + DM);
      uint4 ya = ld_b128(ysrc);
      const float rwin = __uint_as_float(((int)win.x < 0 ? win.x & 0x7fffffffu : ~win.x) & ~0x1ffu);
      const float rs = rbf(rcp(1.f + __expf(-rbf(rwin))));
      uint32_t n = 0;
      while (__any_sync(0xffffffffu, fh.y != tag || fx.y != tag)) { fh = ld_pair(fsrc); fx = ld_pair(fsrc + DM); watchdog(n); }
      while (true) {
        const bool miss = ((ya.x & 1) | (ya.y & 1) << 1) != tag;
        if (!__any_sync(0xffffffffu, miss)) break;
        if (miss) ya = ld_b128(ysrc);
        watchdog(n);
      }
      PROF(8, t3 == 0, 5);
      float y[8] = {bf_lo(ya.x & ~1u), bf_hi(ya.x), bf_lo(ya.y & ~1u), bf_hi(ya.y), bf_lo(ya.z), bf_hi(ya.z), bf_lo(ya.w), bf_hi(ya.w)};
#pragma unroll
      for (int h = 4; h > 0; h >>= 1) {
        const bool up = lane & (h * 2);
#pragma unroll
        for (int e = 0; e < h; e++) y[e] = (up ? y[e + h] : y[e]) + __shfl_xor_sync(0xffffffffu, up ? y[e] : y[e + h], h * 2);
      }
      y[0] += __shfl_xor_sync(0xffffffffu, y[0], 1);
      if (!(lane & 1)) sts1(par + PAR_RED + 64 + t3 * 2, __float_as_uint(y[0]));
      bar_sync(4, 128);
      if (t3 < 8) {
        float y0 = 0.f;
#pragma unroll
        for (int w7 = 0; w7 < 7; w7++) y0 += __uint_as_float(lds1(par + PAR_RED + 64 + w7 * 32 + t3 * 4));
        const uint32_t gv = lds1(par + PAR_CONST + 16 + t3 * 4);
        const uint32_t upd = hmul2(pack_bf(y0, y0), pack_bf(rs, rs));
        const uint32_t r = hadd2(fx.x, hmul2(__byte_perm(gv, gv, 0x3232), hadd2(fh.x, upd)));
        reinterpret_cast<uint16_t*>(P.out)[(size_t)win.y * DM + (b >> 4) * 128 + t3 * 16 + (b & 15)] = (b & 1) ? r >> 16 : r;
        if (b == 0 && t3 == 0) st_relaxed(&g_epoch, epoch + 1);
      }
      PROF(31, t3 == 0, 36);
    }
    cluster_wait();
  } else {
    const int wg = warp >> 2;

    uint32_t tag;
    {
      uint32_t* const pmod = g_modp + rank * 2 * DM + (b >> 1) * 32 + lane;
      uint32_t* const pln = g_ln1 + (rb * 128 + cj * 16 + warp) * 4;
      uint32_t sc[8];
#pragma unroll
      for (int k = 0; k < 8; k++) sc[k] = ldg_nc1(P.c + rank * 512 + warp * 64 + k * 8 + (lane & 3) * 2);
      const uint32_t epoch = ld_relaxed(&g_epoch);
      if (warp == 0) st_relaxed(pmod, 0);
      if (lane == 0) { st_b128(pln, 0, 0, 0, 0); st_b128(pln + 32, 0, 0, 0, 0); }
      asm volatile("setmaxnreg.inc.sync.aligned.u32 232;");
      bar_sync(1, 320);
#pragma unroll
      for (int k = 0; k < 8; k++) sc[k] = pack_bf(silu_f(bf_lo(sc[k])), silu_f(bf_hi(sc[k])));
      keep(sc);
      tag = epoch % 3 + 1;
#pragma unroll
      for (int part = 0; part < 4; part++) {
        if (!(part & 1)) {
          const uint32_t xa = base + (2 + part / 2) * GST_BYTES + warp * 2048 + lane * 16;
          mbar_wait(bar_hx + part * 4, 0);
          float s0 = 0.f, s1 = 0.f, q0 = 0.f, q1 = 0.f;
#pragma unroll
          for (int q = 0; q < 4; q++) {
            const uint4 xv = lds4(xa + q * 512);
            const uint32_t u[4] = {xv.x, xv.y, xv.z, xv.w};
#pragma unroll
            for (int e = 0; e < 4; e++) { const float lo = bf_lo(u[e]), hi = bf_hi(u[e]); s0 += lo; s1 += hi; q0 += lo * lo; q1 += hi * hi; }
          }
          s0 += s1; q0 += q1;
#pragma unroll
          for (int o = 16; o > 0; o >>= 1) { s0 += __shfl_xor_sync(0xffffffffu, s0, o); q0 += __shfl_xor_sync(0xffffffffu, q0, o); }
          const float mean = s0 * (1.f / DM);
          float mb, sd;
          ln_scalars(mean, fmaxf(q0 * (1.f / DM) - mean * mean, 0.f), mb, sd);
          uint32_t ih, il;
          split_inv(sd, ih, il);
          if (lane == 0) st_b128(pln + part * 16, pack_bf(mb, mb), ih, il, tag);
          PROF(1, tid == 0 && part == 2, 4);
        } else if (late == (part == 3)) {
          const uint32_t fr = (lane & 7) + (lane >> 4) * 8, tq = lane & 3;
          const uint32_t wa = stage + warp * 4096 + fr * 64 + ((((lane >> 3) & 1) ^ ((fr >> 1) & 3)) << 4);
          float d0[4] = {0.f, 0.f, 0.f, 0.f}, d1[4] = {0.f, 0.f, 0.f, 0.f};
          mbar_wait(bar_hw, 0);
#pragma unroll
          for (int ks = 0; ks < 4; ks++) {
            uint32_t w[8];
            ldmatrix4t(wa + ks * 1024, w[0], w[1], w[2], w[3]);
            ldmatrix4t((wa ^ 32) + ks * 1024, w[4], w[5], w[6], w[7]);
            mma16816(d0, w[0], w[1], w[2], w[3], sc[2 * ks], sc[2 * ks + 1]);
            mma16816(d1, w[4], w[5], w[6], w[7], sc[2 * ks], sc[2 * ks + 1]);
          }
          sts1(base + 2 * GST_BYTES + warp * 2048 + (tq * 8 + (lane >> 2)) * 4, __float_as_uint((tq & 2) ? ((tq & 1) ? d1[2] : d1[0]) : ((tq & 1) ? d0[2] : d0[0])));
          bar_sync(1, 256);
          if (warp == 0) {
            float s = 0.f;
#pragma unroll
            for (int w8 = 0; w8 < 8; w8++) s += __uint_as_float(lds1(base + 2 * GST_BYTES + w8 * 2048 + lane * 4));
            st_relaxed(pmod, (__float_as_uint(s) & ~3u) | tag);
          }
          PROF(1, tid == 0, 3);
        }
      }
      cluster_wait();
      if (wg == 1) bar_arrive(2, 256);
    }

    float f0 = 0.f, f1 = 0.f;
    const uint32_t rempty = lane < 2 ? mapa(bempty, lane & 1) : 0;
    constexpr uint32_t GE = NSLOT * 8 + 32;
    float o[64], s[64];
#pragma unroll 1
    for (int ps = 0; ps < 3; ps++) {
      {
        const uint32_t xt = ps == 1 ? XT1 : XT2, wt = ps == 1 ? WT1 : WT2;
        const int nst = ps == 2 ? 28 : 14;
        if (ps == 0) {
          float ga[64], gb[64];
#pragma unroll
          for (int i = 0; i < 64; i++) { ga[i] = 0.f; gb[i] = 0.f; }
          uint32_t a[2][16];
          const uint32_t l = fresh_lane();
          uint32_t fa[4];
#pragma unroll
          for (int kk = 0; kk < 4; kk++) fa[kk] = (base + wg * 8192 + frag_offset(warp)) ^ (kk * 32);
          const uint32_t mt = par + (l & 3) * 16;
          auto fetch = [&](int i, uint32_t (&f)[16], uint32_t z) {
            mbar_wait(xfull + (i & 3) * 8, i >> 2);
#pragma unroll
            for (int kk = 0; kk < 4; kk++) ldmatrix4(fa[kk] + (i & 3) * GST_BYTES + z, f[4 * kk], f[4 * kk + 1], f[4 * kk + 2], f[4 * kk + 3]);
          };
          const bool oddw = warp & 2;
          uint4 r0, r1;
          {
            const uint32_t t7 = (warp & 1) * 64 + (l >> 4) * 32 + (l & 15);
            const uint32_t* pm = g_modp + wg * DM + ((cj * 128 + t7 * 4) & (DM - 1));
            const uint32_t* pr = g_ln1 + (rb * 128 + warp * 16 + (l >> 2)) * 4;
            uint4 m0 = make_uint4(tag, tag, tag, tag), m1 = m0;
            if (!oddw) { m0 = ld_relaxed4(pm); m1 = ld_relaxed4(pm + 2 * DM); }
            r0 = ld_b128(pr); r1 = ld_b128(pr + 32);
            fetch(0, a[0], 0); fetch(1, a[1], 0);
            uint32_t n = 0;
            bool written = false;
#pragma unroll 1
            while (true) {
              uint32_t miss;
              asm volatile("{ .reg .pred p0, p1, p2, p3; .reg .b32 t, u;\n"
                           "lop3.b32 t, %1, %2, %19, 0x7e; lop3.b32 u, %3, %4, %19, 0x7e; or.b32 t, t, u; and.b32 t, t, 3; setp.ne.u32 p0, t, 0;\n"
                           "lop3.b32 t, %5, %6, %19, 0x7e; lop3.b32 u, %7, %8, %19, 0x7e; or.b32 t, t, u; and.b32 t, t, 3; setp.ne.u32 p1, t, 0;\n"
                           "setp.ne.u32 p2, %12, %19; setp.ne.u32 p3, %16, %19;\n"
                           "@p0 ld.relaxed.gpu.global.v4.u32 {%1, %2, %3, %4}, [%17];\n"
                           "@p1 ld.relaxed.gpu.global.v4.u32 {%5, %6, %7, %8}, [%17 + 8192];\n"
                           "@p2 ld.relaxed.gpu.global.v4.u32 {%9, %10, %11, %12}, [%18];\n"
                           "@p3 ld.relaxed.gpu.global.v4.u32 {%13, %14, %15, %16}, [%18 + 128];\n"
                           "or.pred p0, p0, p1; or.pred p2, p2, p3; vote.sync.any.pred p0, p0, 0xffffffff; vote.sync.any.pred p2, p2, 0xffffffff;\n"
                           "selp.u32 t, 1, 0, p0; selp.u32 u, 2, 0, p2; or.b32 %0, t, u; }"
                           : "=r"(miss), "+r"(m0.x), "+r"(m0.y), "+r"(m0.z), "+r"(m0.w), "+r"(m1.x), "+r"(m1.y), "+r"(m1.z), "+r"(m1.w),
                             "+r"(r0.x), "+r"(r0.y), "+r"(r0.z), "+r"(r0.w), "+r"(r1.x), "+r"(r1.y), "+r"(r1.z), "+r"(r1.w)
                           : "l"(pm), "l"(pr), "r"(tag) : "memory");
              if (!(miss & 1) && !written) {
                written = true;
                if (!oddw) write_table(par, wg, t7, m0, m1);
                mbar_arrive(bar_mod);
              }
              if (!miss) break;
              watchdog(n);
            }
          }
          const uint32_t zero = r0.w ^ tag;
          auto normalize = [&](uint32_t (&f)[16]) {
#pragma unroll
            for (int k = 0; k < 16; k += 2) { f[k] = ln_norm(f[k], r0.x, r0.y, r0.z); f[k + 1] = ln_norm(f[k + 1], r1.x, r1.y, r1.z); }
          };
          auto modulate = [&](int i, uint32_t (&f)[16]) {
#pragma unroll
            for (int kk = 0; kk < 4; kk++) {
              const uint4 m = lds4(mt + slice_of(i) * 256 + kk * 64);
              f[4 * kk] = hfma2(f[4 * kk], m.x, m.z); f[4 * kk + 1] = hfma2(f[4 * kk + 1], m.x, m.z);
              f[4 * kk + 2] = hfma2(f[4 * kk + 2], m.y, m.w); f[4 * kk + 3] = hfma2(f[4 * kk + 3], m.y, m.w);
            }
            keep(f);
            mbar_arrive_pred(xempty + (i & 3) * 8, l == 0);
          };
          auto publish = [&](int u, uint32_t (&f)[16]) {
#pragma unroll
            for (int kk = 0; kk < 4; kk++) stmatrix4(fa[kk] + OFF_STAGE + u * UNIT, f[4 * kk], f[4 * kk + 1], f[4 * kk + 2], f[4 * kk + 3]);
            __syncwarp();
            mbar_arrive_pred(bar_hpub + u * 8, l == 0);
          };
          auto multiply = [&](int i, uint32_t (&f)[16]) {
            mbar_wait(gfull + (i & 3) * 8, i >> 2);
            const uint64_t db = make_desc(base + (i & 3) * GST_BYTES + UNIT, 8192, 1024);
            wg_fence();
#pragma unroll
            for (int kk = 0; kk < 4; kk++) mma256_rs(ga, gb, f[4 * kk], f[4 * kk + 1], f[4 * kk + 2], f[4 * kk + 3], db + kk * 128);
            wg_commit();
          };
          auto next = [&](int i, uint32_t (&f)[16]) {
            wg_wait<1>();
            mbar_arrive_cl(rempty, GE + ((i + 2) & 3) * 8);
            uint32_t z = zero;
#pragma unroll
            for (int k = 0; k < 16; k += 2) asm volatile("lop3.b32 %0, %1, %2, %0, 0xA8;" : "+r"(z) : "r"(f[k]), "r"(f[k + 1]));
            fetch(i, f, z);
            normalize(f);
            if (i == 2) { keep(f); mbar_wait(bar_mod2, 0); }
            modulate(i, f); multiply(i, f);
          };
          normalize(a[0]); normalize(a[1]);
          keep(a[0]); keep(a[1]);
          mbar_wait(bar_mod, 0);
          PROF(1, tid == 0, 2);
          modulate(0, a[0]); multiply(0, a[0]); publish(0, a[0]);
          modulate(1, a[1]); multiply(1, a[1]);
#pragma unroll 1
          for (int i = 2; i < NRS; i += 2) {
            next(i, a[0]);
            if (i == 2) publish(1, a[0]);
            next(i + 1, a[1]);
          }
          wg_wait<1>();
          mbar_arrive_cl(rempty, GE + ((NRS + 2) & 3) * 8);
#pragma unroll 1
          for (int i = NRS; i < 14; i++) {
            mbar_wait(xfull + (i & 3) * 8, (i >> 2) & 1);
            mbar_wait(gfull + (i & 3) * 8, (i >> 2) & 1);
            const uint32_t xa = base + (i & 3) * GST_BYTES;
            const uint64_t da = make_desc(xa + wg * 8192, 16, 1024), db = make_desc(xa + UNIT, 8192, 1024);
            if (i == 13) bar_sync(2 + wg, 256);
            wg_fence();
#pragma unroll
            for (int kk = 0; kk < 4; kk++) mma256_ss(ga, gb, da + kk * 2, db + kk * 128, 1);
            wg_commit();
            if (i == 13) bar_arrive(3 - wg, 256);
            wg_wait<1>();
            uint32_t z = zero;
#pragma unroll
            for (int k = 0; k < 16; k += 2) asm volatile("lop3.b32 %0, %1, %2, %0, 0xA8;" : "+r"(z) : "r"(a[1][k]), "r"(a[1][k + 1]));
            mbar_arrive_cl(rempty, GE + ((i + 3) & 3) * 8 + z);
            mbar_arrive_pred(xempty + ((i + 3) & 3) * 8, l == 0 && i != NRS);
          }
          mbar_wait(xfull + 16, 1);
          wg_wait<0>();
          keep(ga); keep(gb);
#pragma unroll
          for (int i = 0; i < 64; i++) {
            asm volatile("mov.b32 %0, %1;" : "=f"(s[i]) : "f"(ga[i]));
            asm volatile("mov.b32 %0, %1;" : "=f"(o[i]) : "f"(gb[i]));
          }
        } else {
          float ga[64], gb[64];
#pragma unroll
          for (int i = 0; i < 64; i++) {
            asm volatile("mov.b32 %0, %1;" : "=f"(ga[i]) : "f"(s[i]));
            asm volatile("mov.b32 %0, %1;" : "=f"(gb[i]) : "f"(o[i]));
          }
#pragma unroll 1
          for (int i = 0; i < nst; i++) {
            mbar_wait(gfull + (i & 3) * 8, (i >> 2) & 1);
            const uint64_t da = make_desc(base + unit_of(xt, i & 3) + wg * 8192, 16, 1024), db = make_desc(base + unit_of(wt, i & 3), 8192, 1024);
            if (i == nst - 1) bar_sync(2 + wg, 256);
            wg_fence();
#pragma unroll
            for (int kk = 0; kk < 4; kk++) mma256_ss(ga, gb, da + kk * 2, db + kk * 128, kk ? 1 : i);
            wg_commit();
            if (i == nst - 1) bar_arrive(3 - wg, 256);
            wg_wait<1>();
            mbar_arrive_cl(rempty, GE + ((i + 3) & 3) * 8, i != 0);
            PROF(4, tid == 0 && (i & 3) == 0, 40 + (ps - 1) * 4 + i / 4);
          }
          wg_wait<0>();
          keep(ga); keep(gb);
#pragma unroll
          for (int i = 0; i < 64; i++) {
            asm volatile("mov.b32 %0, %1;" : "=f"(s[i]) : "f"(ga[i]));
            asm volatile("mov.b32 %0, %1;" : "=f"(o[i]) : "f"(gb[i]));
          }
        }
        mbar_arrive_cl(rempty, GE + (ps == 2 ? 24 : 8));
        if (ps == 2) break;
      }
      const uint32_t qw = base + wg * 8192, qt = QT >> (16 * ps), at = ps ? AT1 : AT0;
      {
        const uint32_t wt = ps ? WT1 : WT0;
        const uint64_t da0 = make_desc(qw + unit_of(qt, 2), 16, 1024), da1 = make_desc(qw + unit_of(qt, 3), 16, 1024);
        const uint64_t db0 = make_desc(base + unit_of(wt, 2), 8192, 1024), db1 = make_desc(base + unit_of(wt, 3), 8192, 1024);
        mbar_wait(gfull + 16, 1);
        bar_sync(2 + wg, 256);
        wg_fence();
#pragma unroll
        for (int kk = 0; kk < 4; kk++) mma_ss<1>(s, da0 + kk * 2, db0 + kk * 128, 1);
        wg_commit();
        mbar_wait(xfull + 24, 1);
        mbar_wait(gfull + 24, 1);
        wg_fence();
#pragma unroll
        for (int kk = 0; kk < 4; kk++) mma_ss<1>(s, da1 + kk * 2, db1 + kk * 128, 1);
        wg_commit();
        bar_arrive(3 - wg, 256);
        mbar_wait(ps == 0 ? bar_pread : bar_ofree + 8, 0);
        wg_wait<0>();
        keep(s);
        PROF(2, tid == 0, 8 + ps * 8);
        uint32_t q[32];
        pack_p(s, q);
#pragma unroll
        for (int i = 0; i < 4; i++) stmatrix4((qw + unit_of(qt, 0) + frag_offset(warp)) ^ (i << 5), q[4 * i], q[4 * i + 1], q[4 * i + 2], q[4 * i + 3]);
        keep(q);
        bar_sync(2 + wg, 256);
        wg_fence();
#pragma unroll
        for (int kk = 0; kk < 8; kk++) mma_ss<1>(o, (kk < 4 ? da0 : da1) + (kk & 3) * 2, (kk < 4 ? db0 : db1) + UNIT / 16 + (kk & 3) * 128, 1);
        wg_commit();
        mbar_wait(bfull, 0);
        wg_fence();
        const uint64_t dk = make_desc(base + unit_of(at, 0), 16, 1024);
#pragma unroll
        for (int kk = 0; kk < 8; kk++) mma_rs<0>(s, q[4 * kk], q[4 * kk + 1], q[4 * kk + 2], q[4 * kk + 3], dk + (kk >> 2) * 1024 + (kk & 3) * 2, kk != 0);
        wg_commit();
        bar_arrive(3 - wg, 256);
#pragma unroll
        for (int i = 4; i < 8; i++) stmatrix4((qw + unit_of(qt, 1) + frag_offset(warp)) ^ ((i & 3) << 5), q[4 * i], q[4 * i + 1], q[4 * i + 2], q[4 * i + 3]);
        wg_wait<1>();
        keep(o);
        mbar_arrive_cl(rempty, GE + 16);
        mbar_arrive_cl(rempty, GE + 24);
        store_chunk<0>(o, qw + unit_of(qt, 2) + frag_offset(warp));
        store_chunk<1>(o, qw + unit_of(qt, 3) + frag_offset(warp));
        wg_wait<0>();
        keep(s);
        mbar_arrive_cl(rempty, 0);
      }
      PROF(4, tid == 0 && ps == 1, 61);
      float l0 = 0.f, l1 = 0.f;
      auto step = [&](auto odd_c, const int j, uint32_t (&pw)[32], uint32_t (&pr)[32]) {
        constexpr bool ODD = decltype(odd_c)::value;
        const bool first = !ODD && (j & 2) == 0, last = ODD && j == 7;
        const uint32_t ph = (j >> 1) & 1;
        float i0, i1, a0, a1;
        const bool so = !ODD && j == 4;
        if (so) { i0 = inv_quad_sum(l0); i1 = inv_quad_sum(l1); l0 = 0.f; l1 = 0.f; }
        bool redo = !ODD && (j | ps) == 0;
        while (true) {
          if (redo) {
            float m0 = fmaxf(s[0], s[1]), m1 = fmaxf(s[2], s[3]);
#pragma unroll
            for (int i = 1; i < 16; i++) { m0 = fmaxf(m0, fmaxf(s[4 * i], s[4 * i + 1])); m1 = fmaxf(m1, fmaxf(s[4 * i + 2], s[4 * i + 3])); }
            m0 = fmaxf(m0, __shfl_xor_sync(0xffffffffu, m0, 1)); m1 = fmaxf(m1, __shfl_xor_sync(0xffffffffu, m1, 1));
            m0 = fmaxf(m0, __shfl_xor_sync(0xffffffffu, m0, 2)); m1 = fmaxf(m1, __shfl_xor_sync(0xffffffffu, m1, 2));
            m0 *= SCL2; m1 *= SCL2;
            if (!first) {
              m0 = fmaxf(m0, f0); m1 = fmaxf(m1, f1);
              const float c0 = ex2(f0 - m0), c1 = ex2(f1 - m1);
              l0 *= c0; l1 *= c1;
              wg_wait<0>();
              keep(o);
#pragma unroll
              for (int i = 0; i < 16; i++) { o[4 * i] *= c0; o[4 * i + 1] *= c0; o[4 * i + 2] *= c1; o[4 * i + 3] *= c1; }
            }
            f0 = m0; f1 = m1;
          }
          float b0 = 0.f, b1 = 0.f;
          a0 = 0.f; a1 = 0.f;
#pragma unroll
          for (int i = 0; i < 16; i++) {
            const float e0 = ex2(fmaf(s[4 * i], SCL2, -f0)), e1 = ex2(fmaf(s[4 * i + 1], SCL2, -f0));
            const float e2 = ex2(fmaf(s[4 * i + 2], SCL2, -f1)), e3 = ex2(fmaf(s[4 * i + 3], SCL2, -f1));
            a0 += e0; b0 += e1; a1 += e2; b1 += e3;
            pw[2 * i] = pack_bf(e0, e1); pw[2 * i + 1] = pack_bf(e2, e3);
            if (i == VREL) {
#pragma unroll
              for (int k = 0; k < 2 * VREL + 2; k++) asm volatile("" : "+r"(pw[k])::"memory");
              mbar_wait(bar_mod, 0);
              wg_wait<0>();
              mbar_arrive_cl(rempty, ODD ? 16 : 0, !redo && (ODD || j));
#pragma unroll
              for (int k = 4 * VREL + 4; k < 64; k++) asm volatile("" : "+f"(s[k])::"memory");
            }
          }
          a0 += b0; a1 += b1;
          if (redo) break;
          redo = __any_sync(0xffffffffu, !(a0 + a1 < 0x1p90f) || (!ODD && fminf(a0, a1) < (first ? 0x1p-90f : 0.f)));
          if (!redo) break;
        }
        l0 += a0; l1 += a1;
        keep(pw);
        keep(o);
        if (so) store_chunk<0>(o, i0, i1, qw + unit_of(qt, 0) + frag_offset(warp));
        keep(o);
        if (j == (ODD ? 5 : 0)) { fence_async_smem(); if (ODD) mbar_arrive(bar_ofull + wg * 8); }
        mbar_wait(bfull + (ODD ? 24 : 8), ph);
        bar_sync(2 + wg, 256);
        if (!last) {
          const uint32_t qn = qt >> (j >= 3 ? 8 : 0);
          wg_fence();
          issue_qk(s, qw + unit_of(qn, 0), qw + unit_of(qn, 1), base + unit_of(at, ODD ? 3 : 1));
          wg_commit();
          mbar_wait(bfull + (ODD ? 0 : 16), ODD ? ph ^ 1 : ph);
        }
        if (so) { store_chunk<1>(o, i0, i1, qw + unit_of(qt, 1) + frag_offset(warp)); keep(o); }
        wg_fence();
        issue_pv(o, pw, base + unit_of(at, ODD ? (last ? 3 : 0) : 2), !first);
        wg_commit();
        bar_arrive(3 - wg, 256);
        wg_wait<1>();
        keep(s);
        mbar_arrive_cl(rempty, ODD ? 24 : 8, !last);
        PROF(4, tid == 0 && ps == 1, 51 + j);
      };
      uint32_t pa[32], pb[32];
#pragma unroll 1
      for (int j = 0; j < 8; j += 2) {
        step(std::false_type{}, j, pa, pb);
        step(std::true_type{}, j + 1, pb, pa);
      }
      {
        const float i0 = inv_quad_sum(l0), i1 = inv_quad_sum(l1);
        wg_wait<0>();
        keep(o);
        mbar_arrive_cl(rempty, 24);
        store_chunk<0>(o, i0, i1, qw + unit_of(qt, 2) + frag_offset(warp));
        store_chunk<1>(o, i0, i1, qw + unit_of(qt, 3) + frag_offset(warp));
        fence_async_smem();
        mbar_arrive(bar_ofull + 16 + wg * 8);
      }
      PROF(2, tid == 0, 10 + ps * 8);
    }

    const int ln = fresh_lane(), g = ln >> 2, tq = ln & 3, ct = warp * 32 + ln;
    const bool lane0 = ln == 0;
    const int lrow0 = warp * 16 + g;
    const uint32_t res = base + OFF_RES, trow = res + wg * 8192 + frag_offset(warp);
    uint32_t xr[32];
    uint4 sv[4], own;
    uint32_t* const sg = g_stats + (rb * 8 + warp) * 512 + g * 4;
    uint32_t* sp[4];
#pragma unroll
    for (int k = 0; k < 4; k++) sp[k] = sg + (tq & 1) * 32 + (((tq >> 1) ^ (cj >> 2)) * 4 + (k ^ (cj & 3))) * 64;
    {
      const uint64_t da = make_desc(base + wg * 8192, 16, 1024), db = make_desc(base, 8192, 1024);
      constexpr int U = UNIT / 16;
#define HALF_STAGE(acc, xu, wu) _Pragma("unroll") for (int kk = 0; kk < 4; kk++) mma_ss<1>(acc, da + (xu) * U + kk * 2, db + (wu) * U + kk * 128, 1)
      PROF(10, ct == PT, 19); STAMP(0);
      cluster_arrive();
      mbar_wait(gfull, 1);
      mbar_wait(gfull + 8, 1);
      bar_sync(2 + wg, 256);
      wg_fence();
      HALF_STAGE(o, 7, 1);
      HALF_STAGE(o, 8, 3);
      wg_commit();
      STAMP(16);
      mbar_wait(gfull + 16, 1);
      STAMP(17);
      wg_fence();
      HALF_STAGE(o, 6, 11);
      wg_commit();
      bar_arrive(3 - wg, 256);
      mbar_wait(bar_par, 0);
      uint32_t* xo = g_xch + ((size_t)b * 8 * 256 + ct) * 4;
      const uint32_t* xi = g_xch + ((size_t)(b ^ 2) * 8 * 256 + ct) * 4;
      const uint32_t par1 = (~lds1(par + PAR_CONST + 4) & 1) << 16;
      wg_wait<1>();
      mbar_arrive_pred(bar_rel, lane0);
      wg_wait<0>();
      keep(o);
      mbar_arrive_pred(bar_ring, lane0);
      PROF(8, ct == PT, 20); STAMP(1);
#define SEND(i) st_b128(xo + (i) * 1024, (pack_bf(o[8 * (i)], o[8 * (i) + 1]) & ~0x10000u) | par1, pack_bf(o[8 * (i) + 2], o[8 * (i) + 3]), \
                        pack_bf(o[8 * (i) + 4], o[8 * (i) + 5]), pack_bf(o[8 * (i) + 6], o[8 * (i) + 7]))
#pragma unroll
      for (int i = 0; i < NS1; i++) SEND(i);
      PROF(8, ct == PT, 21); STAMP(2);
      bar_sync(2 + wg, 256);
      wg_fence();
      HALF_STAGE(s, 7, 0);
      HALF_STAGE(s, 8, 2);
      HALF_STAGE(s, 6, 10);
      wg_commit();
      bar_arrive(3 - wg, 256);
      STAMP(18);
      mbar_wait(gfull + 24, 1);
#pragma unroll
      for (int i = NS1; i < 8; i++) SEND(i);
      uint4 v[8];
      STAMP(19);
      mbar_wait(bar_xres, 0);
      wg_wait<0>();
      mbar_arrive_pred(bar_ring + 8, lane0);
      bar_sync(2 + wg, 256);
      STAMP(20);
#pragma unroll
      for (int i = 0; i < LD2; i++) v[i] = ld_b128(xi + i * 1024);
      mbar_wait(bar_xres, 0);
      wg_fence();
      HALF_STAGE(s, 9, 4);
      wg_commit();
      mbar_wait(bar_rx, 0);
      wg_fence();
      HALF_STAGE(s, 1, 5);
      wg_commit();
      bar_arrive(3 - wg, 256);
      STAMP(21);
#pragma unroll
      for (int i = LD2; i < 8; i++) v[i] = ld_b128(xi + i * 1024);
      mbar_wait(bar_xres, 0);
      wg_wait<0>();
      keep(s);
      mbar_arrive_pred(bar_ring + 16, lane0);
      PROF(10, ct == PT, 23); STAMP(4);
#pragma unroll
      for (int i = 0; i < 16; i += 2) ldmatrix4((trow ^ ((i & 7) << 4)) + (i >> 3) * 16384, xr[2 * i], xr[2 * i + 1], xr[2 * i + 2], xr[2 * i + 3]);
      uint32_t ga[16];
      uint4 bw[8];
#pragma unroll
      for (int i = 0; i < 8; i++) {
        if (!(i & 1)) {
          const uint4 t = lds4(par + PAR_SINK + i * 32 + tq * 16);
          ga[2 * i] = t.x; ga[2 * i + 1] = t.y; ga[2 * i + 2] = t.z; ga[2 * i + 3] = t.w;
        }
        bw[i] = lds4(par + PAR_T1 + i * 64 + tq * 16);
        if (!(g & 1)) { bw[i].x = 0x3f803f80u; bw[i].y = 0x3f803f80u; }
      }
      uint32_t pk[32];
      pack_p(s, pk);
      const uint32_t par2 = (~lds1(par + PAR_CONST + 12) & 1) << 16;
      {
        uint32_t n = 0, miss;
        do {
          miss = 0;
#pragma unroll
          for (int i = 0; i < 8; i++) miss |= v[i].x ^ par2;
          miss = __any_sync(0xffffffffu, miss & 0x10000u);
          if (miss) {
#pragma unroll
            for (int i = 0; i < 8; i++)
              asm volatile("{ .reg .pred p; .reg .b32 t; xor.b32 t, %0, %5; and.b32 t, t, 0x10000; setp.ne.u32 p, t, 0;\n"
                           "@p ld.relaxed.gpu.global.v4.u32 {%0, %1, %2, %3}, [%4]; }"
                           : "+r"(v[i].x), "+r"(v[i].y), "+r"(v[i].z), "+r"(v[i].w) : "l"(xi + i * 1024), "r"(par1) : "memory");
          }
          watchdog(n);
        } while (miss);
      }
      PROF(8, ct == PT, 22); STAMP(3);
      float ds[4] = {0.f, 0.f, 0.f, 0.f}, dl[4] = {0.f, 0.f, 0.f, 0.f}, q0[4] = {0.f, 0.f, 0.f, 0.f}, q1[4] = {0.f, 0.f, 0.f, 0.f};
#pragma unroll
      for (int i = 0; i < 8; i++) {
        const uint32_t u0 = hfma2(ga[2 * i], hadd2(pk[4 * i], v[i].x & ~0x10000u), xr[4 * i]);
        const uint32_t u1 = hfma2(ga[2 * i], hadd2(pk[4 * i + 1], v[i].y), xr[4 * i + 1]);
        const uint32_t u2 = hfma2(ga[2 * i + 1], hadd2(pk[4 * i + 2], v[i].z), xr[4 * i + 2]);
        const uint32_t u3 = hfma2(ga[2 * i + 1], hadd2(pk[4 * i + 3], v[i].w), xr[4 * i + 3]);
        xr[4 * i] = u0; xr[4 * i + 1] = u1; xr[4 * i + 2] = u2; xr[4 * i + 3] = u3;
        mma16816(ds, u0, u1, u2, u3, bw[i].x, bw[i].y);
        mma16816(dl, u0, u1, u2, u3, bw[i].z, bw[i].w);
        mma16816(q0, u0, u1, u2, u3, u0, u2);
        mma16816(q1, u0, u1, u2, u3, u1, u3);
      }
      const float sqa = (g & 1) ? q0[1] : q0[0], sqb = (g & 1) ? q1[3] : q1[2], dta = ds[1] + dl[1], dtb = ds[3] + dl[3];
      if (tq == (g >> 1)) {
        st_b128(sg + cj * 64, __float_as_uint(ds[0]), __float_as_uint(sqa), __float_as_uint(dta), tag);
        st_b128(sg + cj * 64 + 32, __float_as_uint(ds[2]), __float_as_uint(sqb), __float_as_uint(dtb), tag);
      }
#pragma unroll
      for (int k = 0; k < 4; k++) sv[k] = ld_b128(sp[k]);
      mbar_wait(bar_xres, 0);
      const float sqc = __shfl_sync(0xffffffffu, sqa, g * 4 + (g >> 1)), sqd = __shfl_sync(0xffffffffu, sqb, g * 4 + (g >> 1));
      own = (tq & 1) ? make_uint4(__float_as_uint(ds[2]), __float_as_uint(sqd), __float_as_uint(dtb), tag)
                     : make_uint4(__float_as_uint(ds[0]), __float_as_uint(sqc), __float_as_uint(dta), tag);
    }
    PROF(8, ct == PT, 29); STAMP(5);
    uint32_t mm, ih, il;
    float rbest;
    uint32_t wf[128];
    const uint32_t frow = (ln & 7) + (ln >> 4) * 8;
    const uint32_t wfo = base + (warp & 1) * 8192 + frow * 64 + ((((ln >> 3) & 1) ^ ((frow >> 1) & 3)) << 4);
#define LOAD_WF(m) _Pragma("unroll") for (int f = 0; f < 16; f++) {                                                   \
      const int r = ((f >> 1) * 4 + (m) * 2 + (f & 1)) * 4;                                                           \
      ldmatrix4t(((wfo + unit_of((m) ? FT_U : FT_G, warp >> 1)) ^ ((f & 1) * 32)) + (f >> 1) * 1024, wf[r], wf[r + 1], wf[r + 2], wf[r + 3]); \
    }
    bool early;
    {
#pragma unroll
      for (int i = 0; i < 16; i += 2) stmatrix4((trow ^ ((i & 7) << 4)) + (i >> 3) * 16384, xr[2 * i], xr[2 * i + 1], xr[2 * i + 2], xr[2 * i + 3]);
      const uint4 cst = lds4(par + PAR_CONST);
      const float A1 = __uint_as_float(cst.x), A2 = __uint_as_float(cst.z);
      uint32_t n = 0;
      early = false;
#pragma unroll 1
      while (true) {
        if (!early && (b >= NFFN || __all_sync(0xffffffffu, mbar_test(bar_box + (warp >> 1) * 8, 0)))) {
          early = true;
          LOAD_WF(0);
          __syncwarp();
          mbar_arrive_pred(bar_gate, lane0);
        }
        uint32_t miss;
        asm volatile("{ .reg .pred p0, p1, p2, p3; .reg .b64 u, v; .reg .b128 w;\n"
                     "setp.ge.u32 p0, %22, 2; setp.ne.and.u32 p0, %4, %21, p0; setp.ne.u32 p1, %8, %21; setp.ne.u32 p2, %12, %21; setp.ne.u32 p3, %16, %21;\n"
                     "@p0 ld.relaxed.gpu.global.v4.u32 {%1, %2, %3, %4}, [%17];\n"
                     "@p1 ld.relaxed.gpu.global.v4.u32 {%5, %6, %7, %8}, [%18];\n"
                     "@p2 ld.relaxed.gpu.global.v4.u32 {%9, %10, %11, %12}, [%19];\n"
                     "@p3 ld.relaxed.gpu.global.v4.u32 {%13, %14, %15, %16}, [%20];\n"
                     "or.pred p0, p0, p1; or.pred p2, p2, p3; or.pred p0, p0, p2; vote.sync.any.pred p0, p0, 0xffffffff; selp.u32 %0, 1, 0, p0; }"
                     : "=r"(miss), "+r"(sv[0].x), "+r"(sv[0].y), "+r"(sv[0].z), "+r"(sv[0].w), "+r"(sv[1].x), "+r"(sv[1].y), "+r"(sv[1].z), "+r"(sv[1].w),
                       "+r"(sv[2].x), "+r"(sv[2].y), "+r"(sv[2].z), "+r"(sv[2].w), "+r"(sv[3].x), "+r"(sv[3].y), "+r"(sv[3].z), "+r"(sv[3].w)
                     : "l"(sp[0]), "l"(sp[1]), "l"(sp[2]), "l"(sp[3]), "r"(tag), "r"(tq) : "memory");
        if (!miss) break;
        watchdog(n);
      }
      const uint4 v0 = tq < 2 ? own : sv[0], v1 = sv[1], v2 = sv[2], v3 = sv[3];
      PROF(8, ct == PT, 30); STAMP(6);
      float su = (__uint_as_float(v0.x) + __uint_as_float(v1.x)) + (__uint_as_float(v2.x) + __uint_as_float(v3.x));
      float sq = (__uint_as_float(v0.y) + __uint_as_float(v1.y)) + (__uint_as_float(v2.y) + __uint_as_float(v3.y));
      float dt = (__uint_as_float(v0.z) + __uint_as_float(v1.z)) + (__uint_as_float(v2.z) + __uint_as_float(v3.z));
      su += __shfl_xor_sync(0xffffffffu, su, 2); sq += __shfl_xor_sync(0xffffffffu, sq, 2); dt += __shfl_xor_sync(0xffffffffu, dt, 2);
      const float m = su * (1.f / DM);
      float mb, sd;
      ln_scalars(m, fmaxf(sq * (1.f / DM) - m * m, 0.f), mb, sd);
      const float inv = rcp(sd);
      rbest = (dt - mb * A1) * inv + A2;
      mm = pack_bf(mb, mb);
      ih = pack_bf(inv, inv);
      const float lo = inv - bf_lo(ih);
      il = pack_bf(lo, lo);
    }
    int ibest;
    {
      const uint32_t bits = __float_as_uint(rbest);
      const uint32_t key = (((int)bits < 0 ? ~bits : bits | 0x80000000u) & ~0x1ffu) | ((127 - lrow0 - (tq & 1) * 8) << 2) | tag;
      sts1(par + PAR_RED + warp * 4, __reduce_max_sync(0xffffffffu, key));
      PROF(8, ct == PT, 38); STAMP(7);
      bar_sync(1, 256);
      const uint4 ka = lds4(par + PAR_RED), kb = lds4(par + PAR_RED + 16);
      const uint32_t k2 = max(max(max(ka.x, ka.y), max(ka.z, ka.w)), max(max(kb.x, kb.y), max(kb.z, kb.w)));
      if (ct < CR && cj == 0) st_relaxed(g_cand + ct * 512 + rb * CS, k2);
      ibest = 127 - ((k2 >> 2) & 127);
    }
    PROF(8, ct == PT, 39); STAMP(8);
    if ((ibest >> 4) == warp) {
      const int src = (ibest & 7) * 4 + ((ibest >> 3) & 1), ch = g * 2;
      const uint32_t cm = __shfl_sync(0xffffffffu, mm, src), ch_ = __shfl_sync(0xffffffffu, ih, src), cl = __shfl_sync(0xffffffffu, il, src);
      const uint32_t xa = res + (ch >> 3) * 16384 + ibest * 128 + (((ch & 7) ^ (ibest & 7)) << 4) + tq * 4;
      const uint32_t x0 = lds1(xa), x1 = lds1(xa ^ 16);
      const uint2 p0 = lds2(par + PAR_T2 + ch * 64 + tq * 16), p1 = lds2(par + PAR_T2 + ch * 64 + 64 + tq * 16);
      uint32_t* dst = g_row + rb * 2 * DM + cj * 128 + ln * 4;
      st_pairs(dst, ln_mod(x0, cm, ch_, cl, p0.x, p0.y), ln_mod(x1, cm, ch_, cl, p1.x, p1.y), tag);
      st_pairs(dst + DM, x0, x1, tag);
      __syncwarp();
    }
    PROF(8, ct == PT, 37); STAMP(9);
    uint32_t wd[64];
    const uint32_t wda = base + unit_of(FT_D, warp >> 1) + (warp & 1) * 8192 + frow * 128 + ((((ln >> 3) & 1) ^ (ln & 7)) << 4);
#define LOAD_WD(f) ldmatrix4t((wda ^ ((((f) >> 1) & 3) * 32)) + ((f) >> 3) * 4096 + ((f) & 1) * 2048, wd[4 * (f)], wd[4 * (f) + 1], wd[4 * (f) + 2], wd[4 * (f) + 3])
    if (!early) {
      if (b < NFFN) mbar_wait(bar_box + (warp >> 1) * 8, 0);
      LOAD_WF(0);
      __syncwarp();
      mbar_arrive_pred(bar_gate, lane0);
    }
    if (b < NFFN) {
      const uint32_t own = base + unit_of(FT_G, warp >> 1) + (warp & 1) * 8192;
      mbar_wait(bar_box + (4 + (warp >> 1)) * 8, 0);
      LOAD_WF(1);
      uint32_t* const ydst = ypart_slot(b, warp * 16 + (tq & 1) * 8 + g);
      PROF(8, ct == PT, 31); STAMP(10);
      bool wdok;
      {
        uint32_t n = 0;
        while (!(wdok = __all_sync(0xffffffffu, mbar_test(bar_box + (8 + (warp >> 1)) * 8, 0))) && !__all_sync(0xffffffffu, mbar_test(bar_sel, 0))) watchdog(n);
      }
      if (wdok) {
#pragma unroll
        for (int f = 0; f < 16; f++) LOAD_WD(f);
      }
      STAMP(11);
      mbar_wait(bar_sel, 0);
      PROF(8, ct == PT, 33); STAMP(12);
      float d[8][4];
#pragma unroll
      for (int i = 0; i < 4; i++) { d[i][0] = 0.f; d[i][1] = 0.f; d[i][2] = 0.f; d[i][3] = 0.f; }
#pragma unroll
      for (int ks = 0; ks < 8; ks++) {
        const uint2 hb = lds2(own + 256 + ks * 32 + tq * 8);
#pragma unroll
        for (int mt = 0; mt < 4; mt++) {
          const int r = ks * 16 + mt * 4;
          mma16816(d[mt], wf[r], wf[r + 1], wf[r + 2], wf[r + 3], hb.x, hb.y);
        }
      }
      sts2(own + (tq * 8 + g) * 8, __float_as_uint((tq & 2) ? ((tq & 1) ? d[1][2] : d[1][0]) : ((tq & 1) ? d[0][2] : d[0][0])),
           __float_as_uint((tq & 2) ? ((tq & 1) ? d[3][2] : d[3][0]) : ((tq & 1) ? d[2][2] : d[2][0])));
      bar_sync(1, 256);
      uint32_t ab[4];
      {
        float G = 0.f, U = 0.f;
        uint2 pv[8];
#pragma unroll
        for (int w8 = 0; w8 < 8; w8++) pv[w8] = lds2(base + ln * 8 + ((FT_G >> (w8 >> 1) * 4) & 15) * UNIT + (w8 & 1) * 8192);
#pragma unroll
        for (int w8 = 0; w8 < 8; w8 += 2) {
          G += __uint_as_float(pv[w8].x) + __uint_as_float(pv[w8 + 1].x);
          U += __uint_as_float(pv[w8].y) + __uint_as_float(pv[w8 + 1].y);
        }
        const float act = rbf(silu_f(rbf(G))) * rbf(U);
        const uint32_t pk = pack_bf(act, __shfl_down_sync(0xffffffffu, act, 1));
#pragma unroll
        for (int i = 0; i < 4; i++) ab[i] = __shfl_sync(0xffffffffu, pk, i * 8 + tq * 2);
      }
      if (!wdok) {
        mbar_wait(bar_box + (8 + (warp >> 1)) * 8, 0);
#pragma unroll
        for (int f = 0; f < 16; f++) LOAD_WD(f);
      }
      PROF(8, ct == PT, 34); STAMP(13);
#pragma unroll
      for (int mt = 0; mt < 8; mt++) {
        d[mt][0] = 0.f; d[mt][1] = 0.f; d[mt][2] = 0.f; d[mt][3] = 0.f;
        mma16816(d[mt], wd[mt * 8], wd[mt * 8 + 1], wd[mt * 8 + 2], wd[mt * 8 + 3], ab[0], ab[1]);
        mma16816(d[mt], wd[mt * 8 + 4], wd[mt * 8 + 5], wd[mt * 8 + 6], wd[mt * 8 + 7], ab[2], ab[3]);
      }
      uint32_t yw[4];
#pragma unroll
      for (int i = 0; i < 4; i++) yw[i] = (tq & 1) ? pack_bf(d[2 * i][2], d[2 * i + 1][2]) : pack_bf(d[2 * i][0], d[2 * i + 1][0]);
      if (tq < 2) st_b128(ydst, (yw[0] & ~1u) | (tag & 1), (yw[1] & ~1u) | (tag >> 1), yw[2], yw[3]);
      PROF(8, ct == PT, 35); STAMP(14);
    }
    mbar_wait(bar_sel, 0);
    mbar_arrive_pred(bar_win, ct == 0);
    const int iwin = lds1(par + PAR_CONST + 60) & 0x7ff;
    const bool cand = (iwin >> 4) == rb * 8 + warp;
    {
      const uint32_t mm0 = __shfl_sync(0xffffffffu, mm, ln & ~1), mm1 = __shfl_sync(0xffffffffu, mm, ln | 1);
      const uint32_t ih0 = __shfl_sync(0xffffffffu, ih, ln & ~1), ih1 = __shfl_sync(0xffffffffu, ih, ln | 1);
      const uint32_t il0 = __shfl_sync(0xffffffffu, il, ln & ~1), il1 = __shfl_sync(0xffffffffu, il, ln | 1);
#pragma unroll 1
      for (int hf = 0; hf < 2; hf++) {
        uint32_t x[16];
#pragma unroll
        for (int i = 0; i < 8; i += 2) ldmatrix4((trow ^ (i << 4)) + hf * 16384, x[2 * i], x[2 * i + 1], x[2 * i + 2], x[2 * i + 3]);
#pragma unroll
        for (int i = 0; i < 8; i++) {
          const uint4 pv = lds4(par + PAR_T2 + (hf * 8 + i) * 64 + tq * 16);
          x[2 * i] = hfma2(hfma2(ln_norm(x[2 * i], mm0, ih0, il0), pv.x, pv.y), pv.z, x[2 * i]);
          x[2 * i + 1] = hfma2(hfma2(ln_norm(x[2 * i + 1], mm1, ih1, il1), pv.x, pv.y), pv.z, x[2 * i + 1]);
        }
#pragma unroll
        for (int i = 0; i < 8; i += 2) stmatrix4((trow ^ (i << 4)) + hf * 16384, x[2 * i], x[2 * i + 1], x[2 * i + 2], x[2 * i + 3]);
        if (!cand) fence_async_smem();
        __syncwarp();
        if (!cand && elect_one()) {
          tma2d_store(&maps.out, res + hf * 16384 + warp * 2048, cj * 128 + hf * 64, rb * 128 + warp * 16);
          asm volatile("cp.async.bulk.commit_group;" ::: "memory");
        }
      }
    }
    if (cand) {
      const int wrow0 = warp * 16;
#pragma unroll 2
      for (int p = 0; p < 8; p++) {
        const int row = 2 * p + (ln >> 4), ch = ln & 15;
        const uint4 v = lds4(res + (ch >> 3) * 16384 + (wrow0 + row) * 128 + (((ch & 7) ^ (row & 7)) << 4));
        if (rb * 128 + wrow0 + row != iwin) *reinterpret_cast<uint4*>(P.out + (size_t)(rb * 128 + wrow0 + row) * DM + cj * 128 + ch * 8) = v;
      }
    }
    asm volatile("cp.async.bulk.wait_group.read 0;" ::: "memory");
    PROF(8, ct == PT, 11); STAMP(15);
    cluster_wait();
  }
}

typedef CUresult (*EncodeFn)(CUtensorMap*, CUtensorMapDataType, cuuint32_t, void*, const cuuint64_t*, const cuuint64_t*,
                             const cuuint32_t*, const cuuint32_t*, CUtensorMapInterleave, CUtensorMapSwizzle,
                             CUtensorMapL2promotion, CUtensorMapFloatOOBfill);

void map2d(EncodeFn enc, CUtensorMap* m, const void* p, uint64_t rows, uint64_t cols, uint32_t brows) {
  cuuint64_t dims[2] = {cols, rows}, strides[1] = {cols * 2};
  cuuint32_t box[2] = {64, brows}, es[2] = {1, 1};
  enc(m, CU_TENSOR_MAP_DATA_TYPE_BFLOAT16, 2, const_cast<void*>(p), dims, strides, box, es, CU_TENSOR_MAP_INTERLEAVE_NONE,
      CU_TENSOR_MAP_SWIZZLE_128B, CU_TENSOR_MAP_L2_PROMOTION_L2_256B, CU_TENSOR_MAP_FLOAT_OOB_FILL_NONE);
}
void map2d_narrow(EncodeFn enc, CUtensorMap* m, const void* p, uint64_t rows, uint64_t cols, uint32_t brows) {
  cuuint64_t dims[2] = {cols, rows}, strides[1] = {cols * 2};
  cuuint32_t box[2] = {32, brows}, es[2] = {1, 1};
  enc(m, CU_TENSOR_MAP_DATA_TYPE_BFLOAT16, 2, const_cast<void*>(p), dims, strides, box, es, CU_TENSOR_MAP_INTERLEAVE_NONE,
      CU_TENSOR_MAP_SWIZZLE_64B, CU_TENSOR_MAP_L2_PROMOTION_L2_64B, CU_TENSOR_MAP_FLOAT_OOB_FILL_NONE);
}
void map3d(EncodeFn enc, CUtensorMap* m, const void* p, uint64_t rows, uint64_t cols, uint32_t brows, uint32_t nch) {
  cuuint64_t dims[3] = {64, rows, cols / 64}, strides[2] = {cols * 2, 128};
  cuuint32_t box[3] = {64, brows, nch}, es[3] = {1, 1, 1};
  enc(m, CU_TENSOR_MAP_DATA_TYPE_BFLOAT16, 3, const_cast<void*>(p), dims, strides, box, es, CU_TENSOR_MAP_INTERLEAVE_NONE,
      CU_TENSOR_MAP_SWIZZLE_128B, CU_TENSOR_MAP_L2_PROMOTION_L2_256B, CU_TENSOR_MAP_FLOAT_OOB_FILL_NONE);
}

}

extern "C" void kernel_launch(void* const* d_in, const int* in_sizes, int n_in, void* d_out, int out_size) {
  (void)in_sizes; (void)n_in; (void)out_size;
  static EncodeFn enc = nullptr;
  if (!enc) {
    void* fn = nullptr;
    cudaDriverEntryPointQueryResult st;
    cudaGetDriverEntryPoint("cuTensorMapEncodeTiled", &fn, cudaEnableDefault, &st);
    enc = (EncodeFn)fn;
    cudaFuncSetAttribute(fused_kernel, cudaFuncAttributeMaxDynamicSharedMemorySize, SMEM_BYTES);
  }
  Maps maps;
  map2d(enc, &maps.x, d_in[0], SEQ, DM, 128);
  map2d(enc, &maps.out, d_out, SEQ, DM, 16);
  map3d(enc, &maps.wq, d_in[3], DM, NQ, 64, 2);
  map3d(enc, &maps.k, d_in[1], 4 * SK, 128, 128, 1);
  map3d(enc, &maps.v, d_in[2], 4 * SK, 128, 128, 1);
  map3d(enc, &maps.wo, d_in[4], NQ, DM, 64, 2);
  map2d_narrow(enc, &maps.wg, d_in[7], DM, FF, 256);
  map2d_narrow(enc, &maps.wu, d_in[8], DM, FF, 256);
  map3d(enc, &maps.wd, d_in[9], FF, DM, 32, 4);
  map2d_narrow(enc, &maps.wm, d_in[11], DM, NMOD, 256);
  Ptrs p;
  p.x = (const __nv_bfloat16*)d_in[0];
  p.w_r = (const __nv_bfloat16*)d_in[6];
  p.w_gate = (const __nv_bfloat16*)d_in[7];
  p.w_up = (const __nv_bfloat16*)d_in[8];
  p.w_down = (const __nv_bfloat16*)d_in[9];
  p.c = (const __nv_bfloat16*)d_in[10];
  p.w_mod = (const __nv_bfloat16*)d_in[11];
  p.out = (__nv_bfloat16*)d_out;
  fused_kernel<<<NMAIN + NHELP, 384, SMEM_BYTES>>>(maps, p);
}
```

```cpp
#include <cuda_runtime.h>
#include <cuda_bf16.h>
#include <cuda.h>
#include <stdint.h>
#include <type_traits>

#define HD 2
#define HDX 2
#define NRS 8
#define OSL 900
#define OSL2 400
#define RSL 40
#define BMAP 2
#define BOFF 6
#define BOF2 6
#define CSH 4
#define VREL 5
#define OPS 8192
#define ODS1 5
#define ODS 7
#define PG0 15
#define WB 2
#define WN 20
#define HU 32
#define RES0 17
#define RES1 20
#define GOST 20
#define NS1 5
#define LD2 4
#define FPACE0 2
#define FPACE 3
#define CR 8
#define CS 8

namespace {

constexpr int SEQ = 2048, DM = 1024, NQ = 4096, SK = 2048, WIN = 512, FF = 3584, NMOD = 6144;
constexpr int NMAIN = 128, NHELP = 4, NFFN = 112;
constexpr int NSLOT = 4, SLOT_BYTES = 32768, UNIT = 16384, GST_BYTES = 3 * UNIT;
constexpr uint32_t XT1 = 0xDCBA, XT2 = 0x9687;
constexpr uint32_t WT0 = 0xA741, WT1 = 0x7420, WT2 = 0x4A20;
constexpr uint32_t AT0 = WT1, AT1 = WT2;
constexpr uint32_t QT = 0xDC9696DC;
constexpr int OFF_STAGE = 12 * UNIT;
constexpr uint32_t FT_G = 0x07B3, FT_U = 0xA628, FT_D = 0x5149;
constexpr int OFF_RES = 12 * UNIT;
constexpr int OFF_PAR = 14 * UNIT;
constexpr int OFF_BAR = OFF_PAR + 2528;
constexpr int SMEM_BYTES = OFF_BAR + 544;
static_assert(SMEM_BYTES <= 232448, "smem");

constexpr int PAR_T1 = 0;
constexpr int PAR_T2 = 512;
constexpr int PAR_CONST = 1536;
constexpr int PAR_RED = 1600;
constexpr int PAR_SINK = 2176;

struct Maps {
  CUtensorMap x, wq, k, v, wo, wg, wu, wd, wm, out;
};
struct Ptrs {
  const __nv_bfloat16 *x, *w_r, *c, *w_mod, *w_gate, *w_up, *w_down;
  __nv_bfloat16* out;
};

__device__ __align__(1024) uint8_t g_act[16 * 80 * UNIT];
__device__ __align__(128) uint32_t g_mod[NMOD];
__device__ __align__(128) uint32_t g_modp[2 * 2 * DM];
__device__ __align__(128) uint32_t g_ln1[SEQ * 4];
__device__ __align__(128) uint32_t g_cnt_h[16 * 32];
__device__ __align__(128) uint32_t g_cnt_o[128 * 32];
__device__ __align__(128) uint32_t g_xch[NMAIN * 8 * 256 * 4];
__device__ __align__(128) uint32_t g_stats[8 * SEQ * 4];
__device__ __align__(128) uint32_t g_cand[CR * 512];
__device__ __align__(128) uint32_t g_row[16 * 2 * DM];
__device__ __align__(128) uint32_t g_ypart[NMAIN * NFFN * 4];
__device__ __forceinline__ uint32_t* ypart_slot(int writer, int reader) { return g_ypart + (writer * NMAIN + reader) * 4; }
__device__ uint32_t g_epoch;

__device__ __forceinline__ uint32_t fresh_lane() { uint32_t l; asm volatile("mov.u32 %0, %%laneid;" : "=r"(l)); return l; }
__device__ __forceinline__ uint32_t frag_offset(int warp) {
  const uint32_t l = fresh_lane();
  return ((warp & 3) * 16 + (l & 15)) * 128 + (((l >> 4) ^ (l & 7)) << 4);
}
__device__ __forceinline__ bool elect_one() {
  uint32_t p;
  asm volatile("{ .reg .pred q; elect.sync _|q, 0xffffffff; selp.u32 %0, 1, 0, q; }" : "=r"(p));
  return p;
}
__device__ __forceinline__ uint32_t smem_u32(const void* p) { return (uint32_t)__cvta_generic_to_shared(p); }
__device__ __forceinline__ void mbar_init(uint32_t bar, uint32_t cnt) {
  asm volatile("mbarrier.init.shared::cta.b64 [%0], %1;" ::"r"(bar), "r"(cnt) : "memory");
}
__device__ __forceinline__ void mbar_expect_tx(uint32_t bar, uint32_t bytes) {
  asm volatile("mbarrier.arrive.expect_tx.shared::cta.b64 _, [%0], %1;" ::"r"(bar), "r"(bytes) : "memory");
}
__device__ __forceinline__ void mbar_arrive(uint32_t bar) {
  asm volatile("mbarrier.arrive.shared::cta.b64 _, [%0];" ::"r"(bar) : "memory");
}
__device__ __forceinline__ void mbar_arrive_pred(uint32_t bar, bool p) {
  asm volatile("{ .reg .pred p; setp.ne.b32 p, %1, 0; @p mbarrier.arrive.shared::cta.b64 _, [%0]; }" ::"r"(bar), "r"((int)p) : "memory");
}
__device__ __forceinline__ void mbar_arrive_cl(uint32_t bar, uint32_t off, bool p = true) {
  asm volatile("{ .reg .pred p, q; .reg .b32 a; setp.ne.b32 q, %2, 0; setp.ne.and.b32 p, %0, 0, q; add.u32 a, %0, %1; @p mbarrier.arrive.shared::cluster.b64 _, [a]; }"
               ::"r"(bar), "r"(off), "r"((int)p) : "memory");
}
__device__ __forceinline__ uint32_t mapa(uint32_t addr, uint32_t cta) {
  uint32_t r; asm("mapa.shared::cluster.u32 %0, %1, %2;" : "=r"(r) : "r"(addr), "r"(cta)); return r;
}
__device__ __forceinline__ void cluster_arrive() { asm volatile("barrier.cluster.arrive.relaxed.aligned;" ::: "memory"); }
__device__ __forceinline__ void cluster_wait() { asm volatile("barrier.cluster.wait.aligned;" ::: "memory"); }
__device__ __forceinline__ void watchdog(uint32_t& n) {
}
__device__ __forceinline__ void mbar_wait(uint32_t bar, uint32_t parity) {
  asm volatile("{\n.reg .pred p;\nWAIT_%=:\nmbarrier.try_wait.parity.shared::cta.b64 p, [%0], %1;\n@!p bra WAIT_%=;\n}" ::"r"(bar), "r"(parity) : "memory");
}
__device__ __forceinline__ bool mbar_test(uint32_t bar, uint32_t parity) {
  uint32_t ok;
  asm volatile("{\n.reg .pred p;\nmbarrier.test_wait.parity.shared::cta.b64 p, [%1], %2;\nselp.u32 %0, 1, 0, p;\n}" : "=r"(ok) : "r"(bar), "r"(parity) : "memory");
  return ok;
}
__device__ __forceinline__ uint64_t l2_stream() {
  uint64_t f; asm("createpolicy.fractional.L2::evict_first.b64 %0, 1.0;" : "=l"(f)); return f;
}
__device__ __forceinline__ uint64_t l2_normal() {
  uint64_t f; asm("createpolicy.fractional.L2::evict_normal.b64 %0, 1.0;" : "=l"(f)); return f;
}
__device__ __forceinline__ void tma2d(uint32_t dst, const CUtensorMap* m, int c0, int c1, uint32_t bar) {
  asm volatile("cp.async.bulk.tensor.2d.shared::cluster.global.mbarrier::complete_tx::bytes.L2::cache_hint [%0], [%1, {%3, %4}], [%2], %5;"
               ::"r"(dst), "l"(m), "r"(bar), "r"(c0), "r"(c1), "l"(l2_stream()) : "memory");
}
__device__ __forceinline__ void bulk_load(uint32_t dst, const void* src, uint32_t bytes, uint32_t bar) {
  asm volatile("cp.async.bulk.shared::cluster.global.mbarrier::complete_tx::bytes [%0], [%1], %2, [%3];" ::"r"(dst), "l"(src), "r"(bytes), "r"(bar) : "memory");
}
__device__ __forceinline__ void bulk_load_stream(uint32_t dst, const void* src, uint32_t bytes, uint32_t bar, uint64_t pol = l2_stream()) {
  asm volatile("cp.async.bulk.shared::cluster.global.mbarrier::complete_tx::bytes.L2::cache_hint [%0], [%1], %2, [%3], %4;"
               ::"r"(dst), "l"(src), "r"(bytes), "r"(bar), "l"(pol) : "memory");
}
__device__ __forceinline__ void tma2d_store(const CUtensorMap* m, uint32_t src, int c0, int c1) {
  asm volatile("cp.async.bulk.tensor.2d.global.shared::cta.bulk_group [%0, {%2, %3}], [%1];" ::"l"(m), "r"(src), "r"(c0), "r"(c1) : "memory");
}
__device__ __forceinline__ void bulk_store(void* dst, uint32_t src, uint32_t bytes) {
  asm volatile("cp.async.bulk.global.shared::cta.bulk_group [%0], [%1], %2;" ::"l"(dst), "r"(src), "r"(bytes) : "memory");
}
__device__ __forceinline__ int slice_of(int i) { return i + ((i & 7) == 1) - ((i & 7) == 2); }
__device__ __forceinline__ uint32_t unit_of(uint32_t table, uint32_t i) { return ((table >> (i * 4)) & 15) * UNIT; }
__device__ __forceinline__ void tma3d(uint32_t dst, const CUtensorMap* m, int c0, int c1, int c2, uint32_t bar) {
  asm volatile("cp.async.bulk.tensor.3d.shared::cluster.global.mbarrier::complete_tx::bytes.L2::cache_hint [%0], [%1, {%3, %4, %5}], [%2], %6;"
               ::"r"(dst), "l"(m), "r"(bar), "r"(c0), "r"(c1), "r"(c2), "l"(l2_stream()) : "memory");
}
template <bool STREAM>
__device__ __forceinline__ void tma3d_mc(uint32_t dst, const CUtensorMap* m, int c0, int c1, int c2, uint32_t bar) {
  if (STREAM)
    asm volatile("cp.async.bulk.tensor.3d.shared::cluster.global.mbarrier::complete_tx::bytes.multicast::cluster.L2::cache_hint [%0], [%1, {%3, %4, %5}], [%2], %6, %7;"
                 ::"r"(dst), "l"(m), "r"(bar), "r"(c0), "r"(c1), "r"(c2), "h"((uint16_t)3), "l"(l2_stream()) : "memory");
  else
    asm volatile("cp.async.bulk.tensor.3d.shared::cluster.global.mbarrier::complete_tx::bytes.multicast::cluster [%0], [%1, {%3, %4, %5}], [%2], %6;"
                 ::"r"(dst), "l"(m), "r"(bar), "r"(c0), "r"(c1), "r"(c2), "h"((uint16_t)3) : "memory");
}
__device__ __forceinline__ void prefetch_map(const CUtensorMap* m) {
  asm volatile("prefetch.tensormap [%0];" ::"l"(m) : "memory");
}
__device__ __forceinline__ void fence_async() { asm volatile("fence.proxy.async.global;" ::: "memory"); }
__device__ __forceinline__ void fence_async_smem() { asm volatile("fence.proxy.async.shared::cta;" ::: "memory"); }
__device__ __forceinline__ void bar_sync(int id, int n) { asm volatile("bar.sync %0, %1;" ::"r"(id), "r"(n) : "memory"); }
__device__ __forceinline__ void bar_arrive(int id, int n) { asm volatile("bar.arrive %0, %1;" ::"r"(id), "r"(n) : "memory"); }
__device__ __forceinline__ void wg_fence() { asm volatile("wgmma.fence.sync.aligned;" ::: "memory"); }
__device__ __forceinline__ void wg_commit() { asm volatile("wgmma.commit_group.sync.aligned;" ::: "memory"); }
template <int N> __device__ __forceinline__ void wg_wait() { asm volatile("wgmma.wait_group.sync.aligned %0;" ::"n"(N) : "memory"); }
__device__ __forceinline__ uint64_t make_desc(uint32_t addr, uint32_t lbo, uint32_t sbo) {
  return (uint64_t)((addr & 0x3FFFF) >> 4) | ((uint64_t)(lbo >> 4) << 16) | ((uint64_t)(sbo >> 4) << 32) | (1ull << 62);
}
__device__ __forceinline__ uint32_t ld_relaxed(const uint32_t* p) {
  uint32_t v; asm volatile("ld.relaxed.gpu.global.u32 %0, [%1];" : "=r"(v) : "l"(p) : "memory"); return v;
}
__device__ __forceinline__ uint32_t ld_acquire(const uint32_t* p) {
  uint32_t v; asm volatile("ld.acquire.gpu.global.u32 %0, [%1];" : "=r"(v) : "l"(p) : "memory"); return v;
}
__device__ __forceinline__ uint4 ld_relaxed4(const uint32_t* p) {
  uint4 v; asm volatile("ld.relaxed.gpu.global.v4.u32 {%0,%1,%2,%3}, [%4];" : "=r"(v.x), "=r"(v.y), "=r"(v.z), "=r"(v.w) : "l"(p) : "memory"); return v;
}
__device__ __forceinline__ void st_relaxed(uint32_t* p, uint32_t v) {
  asm volatile("st.relaxed.gpu.global.u32 [%0], %1;" ::"l"(p), "r"(v) : "memory");
}
__device__ __forceinline__ void st_relaxed4(uint32_t* p, uint32_t a, uint32_t b, uint32_t c, uint32_t d) {
  asm volatile("st.relaxed.gpu.global.v4.u32 [%0], {%1,%2,%3,%4};" ::"l"(p), "r"(a), "r"(b), "r"(c), "r"(d) : "memory");
}
__device__ __forceinline__ void st_b128(uint32_t* p, uint32_t a, uint32_t b, uint32_t c, uint32_t d) {
  asm volatile("{ .reg .b64 u, v; .reg .b128 w; mov.b64 u, {%1, %2}; mov.b64 v, {%3, %4}; mov.b128 w, {u, v}; st.relaxed.gpu.global.b128 [%0], w; }"
               ::"l"(p), "r"(a), "r"(b), "r"(c), "r"(d) : "memory");
}
__device__ __forceinline__ uint4 ld_b128(const uint32_t* p) {
  uint4 r;
  asm volatile("{ .reg .b64 u, v; .reg .b128 w; ld.relaxed.gpu.global.b128 w, [%4]; mov.b128 {u, v}, w; mov.b64 {%0, %1}, u; mov.b64 {%2, %3}, v; }"
               : "=r"(r.x), "=r"(r.y), "=r"(r.z), "=r"(r.w) : "l"(p) : "memory");
  return r;
}
__device__ __forceinline__ void st_pairs(uint32_t* p, uint32_t a, uint32_t b, uint32_t tag) {
  asm volatile("{ .reg .b64 u, v; mov.b64 u, {%1, %3}; mov.b64 v, {%2, %3}; st.relaxed.gpu.global.v2.b64 [%0], {u, v}; }"
               ::"l"(p), "r"(a), "r"(b), "r"(tag) : "memory");
}
__device__ __forceinline__ uint4 ld_pairs(const uint32_t* p) {
  uint4 v;
  asm volatile("{ .reg .b64 u, v; ld.relaxed.gpu.global.v2.b64 {u, v}, [%4]; mov.b64 {%0, %1}, u; mov.b64 {%2, %3}, v; }"
               : "=r"(v.x), "=r"(v.y), "=r"(v.z), "=r"(v.w) : "l"(p) : "memory");
  return v;
}
__device__ __forceinline__ uint2 ld_pair(const uint32_t* p) {
  uint2 v;
  asm volatile("{ .reg .b64 u; ld.relaxed.gpu.global.b64 u, [%2]; mov.b64 {%0, %1}, u; }" : "=r"(v.x), "=r"(v.y) : "l"(p) : "memory");
  return v;
}
__device__ __forceinline__ void red_release(uint32_t* p, uint32_t v) {
  asm volatile("red.release.gpu.global.add.u32 [%0], %1;" ::"l"(p), "r"(v) : "memory");
}
__device__ __forceinline__ uint32_t ldg_nc1(const void* p) {
  uint32_t v;
  asm volatile("ld.global.nc.u32 %0, [%1];" : "=r"(v) : "l"(p));
  return v;
}
__device__ __forceinline__ uint4 ldg_nc4(const void* p) {
  uint4 v; asm volatile("ld.global.nc.L1::no_allocate.v4.u32 {%0,%1,%2,%3}, [%4];" : "=r"(v.x), "=r"(v.y), "=r"(v.z), "=r"(v.w) : "l"(p)); return v;
}
__device__ __forceinline__ uint4 ldg_stream4(const void* p) {
  uint4 v;
  asm volatile("ld.global.nc.L1::no_allocate.L2::cache_hint.v4.u32 {%0,%1,%2,%3}, [%4], %5;" : "=r"(v.x), "=r"(v.y), "=r"(v.z), "=r"(v.w) : "l"(p), "l"(l2_stream()));
  return v;
}
__device__ __forceinline__ void stg4(void* p, uint4 v) {
  asm volatile("st.global.v4.u32 [%0], {%1,%2,%3,%4};" ::"l"(p), "r"(v.x), "r"(v.y), "r"(v.z), "r"(v.w) : "memory");
}
__device__ __forceinline__ void wait_counter(const uint32_t* p, uint32_t target) {
  uint32_t n = 0;
  while (__any_sync(0xffffffffu, (int)(ld_acquire(p) - target) < 0)) { watchdog(n); }
}
__device__ __forceinline__ uint32_t tagf(float v, uint32_t tag) { return (__float_as_uint(v) & ~3u) | tag; }
__device__ __forceinline__ bool tag_ok(uint4 v, uint32_t tag) { return (((v.x ^ tag) | (v.y ^ tag) | (v.z ^ tag) | (v.w ^ tag)) & 3u) == 0; }
__device__ __forceinline__ float untag_sum(uint32_t a, uint32_t b) { return __uint_as_float(a & ~3u) + __uint_as_float(b & ~3u); }
__device__ __forceinline__ uint4 poll4(const uint32_t* p, uint32_t tag) {
  uint4 v = ld_relaxed4(p);
  uint32_t n = 0;
  while (!__all_sync(0xffffffffu, tag_ok(v, tag))) { v = ld_relaxed4(p); watchdog(n); }
  return v;
}
__device__ __forceinline__ float bf_lo(uint32_t v) { return __uint_as_float(v << 16); }
__device__ __forceinline__ float bf_hi(uint32_t v) { return __uint_as_float(v & 0xffff0000u); }
__device__ __forceinline__ uint32_t pack_bf(float lo, float hi) {
  uint32_t r; asm("cvt.rn.bf16x2.f32 %0, %1, %2;" : "=r"(r) : "f"(hi), "f"(lo)); return r;
}
__device__ __forceinline__ float rbf(float v) { return __uint_as_float(pack_bf(0.f, v) & 0xffff0000u); }
__device__ __forceinline__ uint32_t hmul2(uint32_t a, uint32_t b) {
  uint32_t r; asm("mul.rn.bf16x2 %0, %1, %2;" : "=r"(r) : "r"(a), "r"(b)); return r;
}
__device__ __forceinline__ uint32_t hadd2(uint32_t a, uint32_t b) {
  uint32_t r; asm("add.rn.bf16x2 %0, %1, %2;" : "=r"(r) : "r"(a), "r"(b)); return r;
}
__device__ __forceinline__ uint32_t hsub2(uint32_t a, uint32_t b) {
  uint32_t r; asm("sub.rn.bf16x2 %0, %1, %2;" : "=r"(r) : "r"(a), "r"(b)); return r;
}
__device__ __forceinline__ float rcp(float x) { float r; asm("rcp.approx.ftz.f32 %0, %1;" : "=f"(r) : "f"(x)); return r; }
__device__ __forceinline__ float ex2(float x) { float r; asm("ex2.approx.ftz.f32 %0, %1;" : "=f"(r) : "f"(x)); return r; }
__device__ __forceinline__ void stmatrix4(uint32_t addr, uint32_t a, uint32_t b, uint32_t c, uint32_t d) {
  asm volatile("stmatrix.sync.aligned.m8n8.x4.shared.b16 [%0], {%1,%2,%3,%4};" ::"r"(addr), "r"(a), "r"(b), "r"(c), "r"(d) : "memory");
}
__device__ __forceinline__ void ldmatrix4(uint32_t addr, uint32_t& a, uint32_t& b, uint32_t& c, uint32_t& d) {
  asm volatile("ldmatrix.sync.aligned.m8n8.x4.shared.b16 {%0,%1,%2,%3}, [%4];" : "=r"(a), "=r"(b), "=r"(c), "=r"(d) : "r"(addr) : "memory");
}
__device__ __forceinline__ void ldmatrix4t(uint32_t addr, uint32_t& a, uint32_t& b, uint32_t& c, uint32_t& d) {
  asm volatile("ldmatrix.sync.aligned.m8n8.x4.trans.shared.b16 {%0,%1,%2,%3}, [%4];" : "=r"(a), "=r"(b), "=r"(c), "=r"(d) : "r"(addr) : "memory");
}
__device__ __forceinline__ void mma16816(float (&d)[4], uint32_t a0, uint32_t a1, uint32_t a2, uint32_t a3, uint32_t b0, uint32_t b1) {
  asm volatile("mma.sync.aligned.m16n8k16.row.col.f32.bf16.bf16.f32 {%0,%1,%2,%3}, {%4,%5,%6,%7}, {%8,%9}, {%0,%1,%2,%3};"
               : "+f"(d[0]), "+f"(d[1]), "+f"(d[2]), "+f"(d[3]) : "r"(a0), "r"(a1), "r"(a2), "r"(a3), "r"(b0), "r"(b1));
}
__device__ __forceinline__ void sts1(uint32_t a, uint32_t v) { asm volatile("st.shared.u32 [%0], %1;" ::"r"(a), "r"(v) : "memory"); }
__device__ __forceinline__ uint4 lds4(uint32_t a) {
  uint4 v; asm volatile("ld.shared.v4.u32 {%0,%1,%2,%3}, [%4];" : "=r"(v.x), "=r"(v.y), "=r"(v.z), "=r"(v.w) : "r"(a) : "memory"); return v;
}
__device__ __forceinline__ uint2 lds2(uint32_t a) {
  uint2 v; asm volatile("ld.shared.v2.u32 {%0,%1}, [%2];" : "=r"(v.x), "=r"(v.y) : "r"(a) : "memory"); return v;
}
__device__ __forceinline__ uint32_t lds1(uint32_t a) {
  uint32_t v; asm volatile("ld.shared.u32 %0, [%1];" : "=r"(v) : "r"(a) : "memory"); return v;
}
__device__ __forceinline__ void sts2(uint32_t a, uint32_t x, uint32_t y) { asm volatile("st.shared.v2.u32 [%0], {%1,%2};" ::"r"(a), "r"(x), "r"(y) : "memory"); }
__device__ __forceinline__ void sts4(uint32_t a, uint4 v) {
  asm volatile("st.shared.v4.u32 [%0], {%1,%2,%3,%4};" ::"r"(a), "r"(v.x), "r"(v.y), "r"(v.z), "r"(v.w) : "memory");
}
__device__ __forceinline__ float silu_f(float v) { return __fdividef(v, 1.f + __expf(-v)); }
__device__ __forceinline__ uint32_t hfma2(uint32_t a, uint32_t b, uint32_t c) {
  uint32_t r; asm("fma.rn.bf16x2 %0, %1, %2, %3;" : "=r"(r) : "r"(a), "r"(b), "r"(c)); return r;
}
__device__ __forceinline__ void split_inv(float sd, uint32_t& ih, uint32_t& il) {
  const float inv = rcp(sd);
  ih = pack_bf(inv, inv);
  const float lo = inv - bf_lo(ih);
  il = pack_bf(lo, lo);
}
__device__ __forceinline__ uint32_t ln_norm(uint32_t x, uint32_t mean2, uint32_t ih, uint32_t il) {
  const uint32_t d = hsub2(x, mean2);
  return hfma2(d, ih, hmul2(d, il));
}
__device__ __forceinline__ uint32_t ln_mod(uint32_t x, uint32_t mean2, uint32_t ih, uint32_t il, uint32_t c1, uint32_t sh) {
  return hadd2(hmul2(ln_norm(x, mean2, ih, il), c1), sh);
}

#define R8(a, i) "+f"(a[i]), "+f"(a[i + 1]), "+f"(a[i + 2]), "+f"(a[i + 3]), "+f"(a[i + 4]), "+f"(a[i + 5]), "+f"(a[i + 6]), "+f"(a[i + 7])
#define D64 "{%0,%1,%2,%3,%4,%5,%6,%7,%8,%9,%10,%11,%12,%13,%14,%15,%16,%17,%18,%19,%20,%21,%22,%23,%24,%25,%26,%27,%28,%29,%30,%31," \
            "%32,%33,%34,%35,%36,%37,%38,%39,%40,%41,%42,%43,%44,%45,%46,%47,%48,%49,%50,%51,%52,%53,%54,%55,%56,%57,%58,%59,%60,%61,%62,%63}"
template <int TB>
__device__ __forceinline__ void mma_ss(float (&d)[64], uint64_t da, uint64_t db, int sc) {
  asm volatile("{\n.reg .pred p;\nsetp.ne.b32 p, %66, 0;\n"
               "wgmma.mma_async.sync.aligned.m64n128k16.f32.bf16.bf16 " D64 ", %64, %65, p, 1, 1, 0, %67;\n}"
               : R8(d, 0), R8(d, 8), R8(d, 16), R8(d, 24), R8(d, 32), R8(d, 40), R8(d, 48), R8(d, 56)
               : "l"(da), "l"(db), "r"(sc), "n"(TB));
}
template <int TB>
__device__ __forceinline__ void mma_rs(float (&d)[64], uint32_t a0, uint32_t a1, uint32_t a2, uint32_t a3, uint64_t db, int sc) {
  asm volatile("{\n.reg .pred p;\nsetp.ne.b32 p, %69, 0;\n"
               "wgmma.mma_async.sync.aligned.m64n128k16.f32.bf16.bf16 " D64 ", {%64,%65,%66,%67}, %68, p, 1, 1, %70;\n}"
               : R8(d, 0), R8(d, 8), R8(d, 16), R8(d, 24), R8(d, 32), R8(d, 40), R8(d, 48), R8(d, 56)
               : "r"(a0), "r"(a1), "r"(a2), "r"(a3), "l"(db), "r"(sc), "n"(TB));
}
#define D128 "{%0,%1,%2,%3,%4,%5,%6,%7,%8,%9,%10,%11,%12,%13,%14,%15,%16,%17,%18,%19,%20,%21,%22,%23,%24,%25,%26,%27,%28,%29,%30,%31," \
             "%32,%33,%34,%35,%36,%37,%38,%39,%40,%41,%42,%43,%44,%45,%46,%47,%48,%49,%50,%51,%52,%53,%54,%55,%56,%57,%58,%59,%60,%61,%62,%63," \
             "%64,%65,%66,%67,%68,%69,%70,%71,%72,%73,%74,%75,%76,%77,%78,%79,%80,%81,%82,%83,%84,%85,%86,%87,%88,%89,%90,%91,%92,%93,%94,%95," \
             "%96,%97,%98,%99,%100,%101,%102,%103,%104,%105,%106,%107,%108,%109,%110,%111,%112,%113,%114,%115,%116,%117,%118,%119,%120,%121,%122,%123,%124,%125,%126,%127}"
#define R128(d, e) R8(d, 0), R8(d, 8), R8(d, 16), R8(d, 24), R8(d, 32), R8(d, 40), R8(d, 48), R8(d, 56), \
                   R8(e, 0), R8(e, 8), R8(e, 16), R8(e, 24), R8(e, 32), R8(e, 40), R8(e, 48), R8(e, 56)
__device__ __forceinline__ void mma256_ss(float (&d)[64], float (&e)[64], uint64_t da, uint64_t db, int sc) {
  asm volatile("{\n.reg .pred p;\nsetp.ne.b32 p, %130, 0;\n"
               "wgmma.mma_async.sync.aligned.m64n256k16.f32.bf16.bf16 " D128 ", %128, %129, p, 1, 1, 0, 1;\n}"
               : R128(d, e) : "l"(da), "l"(db), "r"(sc));
}
__device__ __forceinline__ void mma256_rs(float (&d)[64], float (&e)[64], uint32_t a0, uint32_t a1, uint32_t a2, uint32_t a3, uint64_t db) {
  asm volatile("{\n.reg .pred p;\nsetp.ne.b32 p, 1, 0;\n"
               "wgmma.mma_async.sync.aligned.m64n256k16.f32.bf16.bf16 " D128 ", {%128,%129,%130,%131}, %132, p, 1, 1, 1;\n}"
               : R128(d, e) : "r"(a0), "r"(a1), "r"(a2), "r"(a3), "l"(db));
}
template <int N> __device__ __forceinline__ void keep(float (&a)[N]) {
#pragma unroll
  for (int i = 0; i < N; i++) asm volatile("" : "+f"(a[i])::"memory");
}
template <int N> __device__ __forceinline__ void keep(uint32_t (&a)[N]) {
#pragma unroll
  for (int i = 0; i < N; i++) asm volatile("" : "+r"(a[i])::"memory");
}

#define STAMP(idx) do {} while (0)
#define PROF(grp, cond, idx) do {} while (0)

constexpr float SCL2 = 1.4426950408889634f * 0.08838834764831845f;

__device__ __forceinline__ void pack_p(const float (&s)[64], uint32_t (&p)[32]) {
#pragma unroll
  for (int i = 0; i < 32; i++) p[i] = pack_bf(s[2 * i], s[2 * i + 1]);
}

__device__ __forceinline__ void issue_qk(float (&s)[64], uint32_t q0, uint32_t q1, uint32_t kslot) {
  const uint64_t db = make_desc(kslot, 16, 1024), da0 = make_desc(q0, 16, 1024), da1 = make_desc(q1, 16, 1024);
#pragma unroll
  for (int kk = 0; kk < 8; kk++) mma_ss<0>(s, (kk < 4 ? da0 : da1) + (kk & 3) * 2, db + (kk >> 2) * 1024 + (kk & 3) * 2, kk != 0);
}
__device__ __forceinline__ void issue_pv(float (&o)[64], uint32_t (&p)[32], uint32_t vslot, int acc) {
  uint64_t db = make_desc(vslot, 16384, 1024);
#pragma unroll
  for (int kk = 0; kk < 8; kk++)
    mma_rs<1>(o, p[4 * kk], p[4 * kk + 1], p[4 * kk + 2], p[4 * kk + 3], db + kk * 128, kk == 0 ? acc : 1);
}

template <int H>
__device__ __forceinline__ void store_chunk(const float (&a)[64], uint32_t addr) {
#pragma unroll
  for (int i = 8 * H; i < 8 * H + 8; i += 2)
    stmatrix4(addr ^ ((i & 7) << 4), pack_bf(a[4 * i], a[4 * i + 1]), pack_bf(a[4 * i + 2], a[4 * i + 3]),
              pack_bf(a[4 * i + 4], a[4 * i + 5]), pack_bf(a[4 * i + 6], a[4 * i + 7]));
}
template <int H>
__device__ __forceinline__ void store_chunk(const float (&a)[64], float i0, float i1, uint32_t addr) {
#pragma unroll
  for (int i = 8 * H; i < 8 * H + 8; i += 2)
    stmatrix4(addr ^ ((i & 7) << 4), pack_bf(a[4 * i] * i0, a[4 * i + 1] * i0), pack_bf(a[4 * i + 2] * i1, a[4 * i + 3] * i1),
              pack_bf(a[4 * i + 4] * i0, a[4 * i + 5] * i0), pack_bf(a[4 * i + 6] * i1, a[4 * i + 7] * i1));
}
__device__ __forceinline__ float inv_quad_sum(float l) {
  l += __shfl_xor_sync(0xffffffffu, l, 1);
  l += __shfl_xor_sync(0xffffffffu, l, 2);
  return rcp(l);
}

__device__ __forceinline__ void write_table(uint32_t table, bool ca, uint32_t t, const uint4& m0, const uint4& m1) {
  float c0 = untag_sum(m0.x, m1.x), c1 = untag_sum(m0.y, m1.y), c2 = untag_sum(m0.z, m1.z), c3 = untag_sum(m0.w, m1.w);
  if (ca) { c0 = 1.f + rbf(c0); c1 = 1.f + rbf(c1); c2 = 1.f + rbf(c2); c3 = 1.f + rbf(c3); }
  const uint32_t d = table + (t >> 2) * 64 + (t & 1) * 32 + (t & 2) * 2 + (ca ? 0 : 8);
  sts1(d, pack_bf(c0, c1));
  sts1(d + 16, pack_bf(c2, c3));
}

__device__ __forceinline__ void ln_scalars(float mean, float var, float& mb, float& sd) {
  mb = rbf(mean);
  float r; asm("sqrt.approx.ftz.f32 %0, %1;" : "=f"(r) : "f"(rbf(rbf(var) + 1e-5f)));
  sd = rbf(r);
}

__global__ void __cluster_dims__(2, 1, 1) __launch_bounds__(384, 1) fused_kernel(const __grid_constant__ Maps maps, const Ptrs P) {
  extern __shared__ __align__(1024) uint8_t smem_raw[];
  const uint32_t base = smem_u32(smem_raw);
  const int tid = threadIdx.x, lane = tid & 31;
  const int warp = __shfl_sync(0xffffffffu, tid >> 5, 0);
  int b = blockIdx.x;
  if (BMAP == 1 && b < NMAIN) b = ((b >> 1) & 7) << 4 | (b >> 4) << 1 | (b & 1);
  if (BMAP == 2 && b < NMAIN) {
    const int p = b >> 1;
    int g, k;
    if (p < 4) { g = 7; k = 4 + p; }
    else if (p < 36) { g = (p - 4 + BOFF) & 7; k = (p - 4) >> 3; }
    else { g = (p - 36 + BOF2) % 7; k = 4 + (p - 36) / 7; }
    b = g << 4 | k << 1 | (b & 1);
  }
  PROF(31, tid == 0, 0);

  if (b >= NMAIN) {
    float* sc = reinterpret_cast<float*>(smem_raw);
    float* red = sc + DM;
    for (int k = tid; k < DM; k += 384) sc[k] = rbf(silu_f(__bfloat162float(P.c[k])));
    __syncthreads();
    if (tid < 256) {
      const int col = 2048 + (b - NMAIN) * 1024 + (tid & 127) * 8, r0 = (tid >> 7) * 512;
      float acc[8];
#pragma unroll
      for (int e = 0; e < 8; e++) acc[e] = 0.f;
#pragma unroll 1
      for (int r = r0; r < r0 + 512; r += HU) {
        uint4 w[HU];
#pragma unroll
        for (int u = 0; u < HU; u++) w[u] = ldg_stream4(P.w_mod + (size_t)(r + u) * NMOD + col);
#pragma unroll
        for (int u = 0; u < HU; u++) {
          float s = sc[r + u];
          acc[0] += s * bf_lo(w[u].x); acc[1] += s * bf_hi(w[u].x); acc[2] += s * bf_lo(w[u].y); acc[3] += s * bf_hi(w[u].y);
          acc[4] += s * bf_lo(w[u].z); acc[5] += s * bf_hi(w[u].z); acc[6] += s * bf_lo(w[u].w); acc[7] += s * bf_hi(w[u].w);
        }
      }
      if (tid >= 128) {
#pragma unroll
        for (int e = 0; e < 8; e++) red[(tid & 127) * 8 + e] = acc[e];
      }
      const uint32_t tag = ld_relaxed(&g_epoch) % 3 + 1;
      bar_sync(1, 256);
      if (tid < 128) {
        uint32_t o[8];
#pragma unroll
        for (int e = 0; e < 8; e++) o[e] = __float_as_uint(rbf(acc[e] + red[tid * 8 + e])) | tag;
        st_relaxed4(g_mod + col, o[0], o[1], o[2], o[3]);
        st_relaxed4(g_mod + col + 4, o[4], o[5], o[6], o[7]);
        const uint4 wr = ldg_nc4(P.w_r + tid * 8);
        const uint32_t wv[4] = {wr.x, wr.y, wr.z, wr.w};
        float dsum = 0.f;
#pragma unroll
        for (int e = 0; e < 8; e++) {
          const float m = bf_hi(o[e]);
          dsum += (b == NMAIN + 2 ? rbf(1.f + m) : m) * ((e & 1) ? bf_hi(wv[e >> 1]) : bf_lo(wv[e >> 1]));
        }
#pragma unroll
        for (int k = 16; k > 0; k >>= 1) dsum += __shfl_xor_sync(0xffffffffu, dsum, k);
        if (lane == 0) st_relaxed(g_mod + (b - NMAIN) * 4 + warp, tagf(dsum, tag));
      }
    }
    PROF(2, tid == 0, 1);
    return;
  }

  const int rank = b & 1;
  const int rb = ((b >> 4) << 1) | rank, cj = (b >> 1) & 7;
  const bool late = b & 4;
  const uint32_t bfull = base + OFF_BAR, bempty = bfull + NSLOT * 8;
  const uint32_t gfull = bempty + NSLOT * 8, gempty = gfull + 32;
  const uint32_t bar_ofull = gempty + 32;
  const uint32_t bar_ofree = bar_ofull + 32;
  const uint32_t bar_par = bar_ofree + 32;
  const uint32_t bar_mod = bar_par + 8;
  const uint32_t bar_pread = bar_mod + 8;
  const uint32_t bar_xres = bar_pread + 8;
  const uint32_t bar_ring = bar_xres + 8;
  const uint32_t bar_box = bar_ring + 24;
  const uint32_t bar_go = bar_box + 96;
  const uint32_t bar_go2 = bar_go + 16;
  const uint32_t bar_cnt = bar_go + 24;
  const uint32_t xfull = bar_go + 40, xempty = xfull + 32;
  const uint32_t bar_hw = xempty + 32, bar_hx = bar_hw + 8;
  const uint32_t bar_hpub = bar_hx + 16;
  const uint32_t bar_win = bar_hpub + 16;
  const uint32_t bar_rx = bar_win + 8;
  const uint32_t bar_sel = bar_rx + 8;
  const uint32_t bar_gate = bar_sel + 8;
  const uint32_t bar_rel = bar_gate + 8;
  const uint32_t bar_od = bar_rel + 8;
  const uint32_t bar_mod2 = bar_od + 8;
  const uint32_t bar_res = bar_go + 8;
  const uint32_t stage = base + OFF_STAGE, par = base + OFF_PAR;

  if (warp == 10 && elect_one()) prefetch_map(&maps.wm);
  if (warp == 8 && elect_one()) {
    for (int s = 0; s < NSLOT; s++) { mbar_init(bfull + s * 8, 1); mbar_init(bempty + s * 8, 16); }
    for (int s = 0; s < 4; s++) { mbar_init(gfull + s * 8, 1); mbar_init(gempty + s * 8, 16); mbar_init(xfull + s * 8, 1); mbar_init(xempty + s * 8, 8); mbar_init(bar_ofree + s * 8, 1); mbar_init(bar_ofull + s * 8, 128); }
    mbar_init(bar_par, 64); mbar_init(bar_mod, 256); mbar_init(bar_pread, 2); mbar_init(bar_xres, 1);
    mbar_init(bar_ring, 8); mbar_init(bar_ring + 8, 8); mbar_init(bar_ring + 16, 8);
    mbar_init(bar_go, 1); mbar_init(bar_go2, 1); mbar_init(bar_cnt, 1); mbar_init(bar_cnt + 8, 1); mbar_init(bar_hpub, 8); mbar_init(bar_hpub + 8, 8); mbar_init(bar_res, 1); mbar_init(bar_win, 1); mbar_init(bar_rx, 1); mbar_init(bar_sel, 64); mbar_init(bar_gate, 8); mbar_init(bar_rel, 8); mbar_init(bar_od, 1); mbar_init(bar_mod2, 64);
    for (int s = 0; s < 12; s++) mbar_init(bar_box + s * 8, 1);
    asm volatile("fence.mbarrier_init.release.cluster;" ::: "memory");
    prefetch_map(&maps.x); prefetch_map(&maps.wq); prefetch_map(&maps.k); prefetch_map(&maps.v);
  }
  if (warp == 9 && elect_one()) {
    mbar_init(bar_hw, 1); mbar_init(bar_hx, 1); mbar_init(bar_hx + 8, 1);
    asm volatile("fence.mbarrier_init.release.cluster;" ::: "memory");
    mbar_expect_tx(bar_hw, 32768);
    mbar_expect_tx(bar_hx, 16384);
    mbar_expect_tx(bar_hx + 8, 16384);
    const __nv_bfloat16* xs = P.x + (size_t)(rb * 128 + cj * 16) * DM;
    bulk_load(base + 2 * GST_BYTES, xs, 16384, bar_hx);
    if (!late) {
      tma2d(stage, &maps.wm, (b >> 1) * 32, rank * 512, bar_hw);
      tma2d(stage + 16384, &maps.wm, (b >> 1) * 32, rank * 512 + 256, bar_hw);
    }
    bulk_load(base + 3 * GST_BYTES, xs + 8 * DM, 16384, bar_hx + 8);
  }
  cluster_arrive();

  if (warp >= 8) {
    asm volatile("setmaxnreg.dec.sync.aligned.u32 40;");
    if (warp < 10) bar_arrive(1, 320);
    const uint32_t epoch = ld_relaxed(&g_epoch);
    cluster_wait();
    if (warp == 8) {
      const int kvrow = (cj >> 1) * SK + (SK - WIN);
      int wch = cj * 8 + rank * 2;
#pragma unroll 1
      for (int ps = 0; ps < 3; ps++) {
        const CUtensorMap* mw = ps == 2 ? &maps.wo : &maps.wq;
        const uint32_t xt = ps == 1 ? XT1 : XT2, wt = ps == 0 ? WT0 : (ps == 1 ? WT1 : WT2);
        const int nst = ps == 2 ? 32 : 16;
#pragma unroll 1
        for (int i = 0; i < nst; i++) {
          const uint32_t bf = gfull + (i & 3) * 8;
          const int kt = ps == 2 ? (((cj & 1) * 4 + ((i >> 1) & 3)) * 4 + (i >> 3)) * 2 + (i & 1) : (ps ? i : slice_of(i) + (b & 14)) & 15;
          const uint32_t wd = base + unit_of(wt, i & 3) + rank * UNIT, xd = base + unit_of(xt, i & 3);
          const uint8_t* xs = g_act + (uint32_t)(rb * 80 + (ps - 1) * 16 + kt) * UNIT;
          if (ps == 0 && i == HD) mbar_wait(bar_mod, 0);
          if (ps == 2 && (i & 7) == 0 && i != 8) mbar_wait(i ? bar_cnt + i - 16 : bar_ofree + 24, 0);
          if ((i & 7) == 0) fence_async();
          if (i == RES0) mbar_wait(bar_res, 0);
          mbar_wait(bf, ((i >> 2) & 1) ^ 1);
          if (elect_one()) {
            mbar_expect_tx(bf, ps ? GST_BYTES : 2 * UNIT);
            if (ps && i < 2) bulk_load_stream(xd, xs, UNIT, bf);
            mbar_arrive_pred(bar_go, i == GOST);
            mbar_arrive_pred(bar_go2, ps == 1 && i == PG0);
            mbar_arrive_pred(bar_od, ps && i == (ps == 1 ? ODS1 : ODS) + 1);
            if (i == RES0) mbar_expect_tx(bar_xres, 32768);
          }
          const int wk = (i == 31 ? kt ^ (rank * 32) : kt) * 64, wc = i == 31 ? cj * 2 : wch;
          const uint64_t xp = i == 31 ? l2_normal() : l2_stream();
          mbar_wait(ps && i < 4 ? bempty + i * 8 : gempty + (i & 3) * 8, ((i >> 2) & 1) ^ 1);
          if (elect_one()) {
            tma3d_mc<true>(wd, mw, 0, wk, wc, bf);
            if (ps && i > 2) bulk_load_stream(xd, xs, UNIT, bf, xp);
            if (i == RES0 || i == RES1) tma2d(base + OFF_RES + (i == RES1) * UNIT, &maps.x, cj * 128 + (i == RES1) * 64, rb * 128, bar_xres);
          }
          if (ps && i == 2) {
            mbar_wait(bar_ofree + (ps - 1) * 16, 0);
            if (elect_one()) bulk_load_stream(xd, xs, UNIT, bf);
          }
        }
        if (ps == 2) break;
        wch = ps ? ((wch >> 3) ^ rank) * 2 : wch + 4;
#pragma unroll 1
        for (int u = 0; u < 16; u++) {
          const bool isk = (u == 0) || ((u & 1) && u < 15);
          const int blk = (isk ? (u + 1) >> 1 : (u == 15 ? 7 : (u >> 1) - 1)) & 3;
          const uint32_t sl = base + unit_of(ps ? AT1 : AT0, u & 3) + rank * UNIT, bf = bfull + (u & 3) * 8;
          mbar_wait(bf, ((u >> 2) & 1) ^ 1);
          if (elect_one()) mbar_expect_tx(bf, SLOT_BYTES);
          mbar_wait(u < 4 ? gempty + ((u + 1) >> 1) * 8 : bempty + (u & 3) * 8, ((u >> 2) & 1) ^ 1);
          if (elect_one()) {
            if (ps && u >= 7 && u != 8) tma3d_mc<true>(sl, isk ? &maps.k : &maps.v, 0, kvrow + blk * 128, rank, bf);
            else tma3d_mc<false>(sl, isk ? &maps.k : &maps.v, 0, kvrow + blk * 128, rank, bf);
          }
        }
      }
      if (elect_one()) mbar_expect_tx(bar_rx, UNIT);
      mbar_wait(bar_rel, 0);
      if (elect_one()) {
        bulk_load_stream(base + UNIT, g_act + (uint32_t)(rb * 80 + 16 + 63 - (cj & 1) * 32) * UNIT, UNIT, bar_rx);
      }
      if (b < NFFN) {
#pragma unroll 1
        for (int u = 0; u < 12; u++) {
          const uint32_t dst = base + unit_of(u < 4 ? FT_G : (u < 8 ? FT_U : FT_D), u & 3);
          if (elect_one()) mbar_expect_tx(bar_box + u * 8, UNIT);
          if (u == 0 || u == 2 || u == 8) mbar_wait(bar_ring + (u == 8 ? 16 : u * 4), 0);
          const int fp = u < 8 ? FPACE0 : FPACE;
          if (u >= fp) mbar_wait(bar_box + (u - fp) * 8, 0);
          if (elect_one()) {
            if (u < 8) tma2d(dst, u < 4 ? &maps.wg : &maps.wu, b * 32, (u & 3) * 256, bar_box + u * 8);
            else tma3d(dst, &maps.wd, 0, b * 32, (u - 8) * 4, bar_box + u * 8);
          }
        }
      }
    } else if (warp == 9) {
      const uint32_t target = 8 * (epoch + 1);
      uint32_t hmask = 0;
#pragma unroll 1
      for (int i = 0; i < 16; i++) {
        if (i == HDX) mbar_wait(bar_mod, 0);
        const int kt = (2 * cj + slice_of(i)) & 15;
        const uint32_t need = i == 15 ? 0xffffu : 1u << kt;
        if (i >= NRS && (hmask & need) != need) {
          uint32_t n = 0;
          do { hmask = __ballot_sync(0xffffffffu, ld_acquire(&g_cnt_h[rb * 32 + (lane & 15)]) == epoch + 1); watchdog(n); } while ((hmask & need) != need);
          PROF(1, lane == 0 && i == NRS, 26);
          fence_async();
        }
        mbar_wait(xempty + (i & 3) * 8, ((i >> 2) & 1) ^ 1);
        if (elect_one()) {
          mbar_expect_tx(xfull + (i & 3) * 8, UNIT);
          if (i < NRS) tma2d(base + (i & 3) * GST_BYTES, &maps.x, kt * 64, rb * 128, xfull + (i & 3) * 8);
          else bulk_load_stream(base + (i & 3) * GST_BYTES, g_act + (uint32_t)(rb * 80 + kt) * UNIT, UNIT, xfull + (i & 3) * 8);
        }
      }
      prefetch_map(&maps.wo);
#pragma unroll 1
      for (int t = 0; t < 4; t++) {
        if (t & 1) mbar_wait(bar_od, t >> 1);
        const int ops = OPS >> (t & 1);
#pragma unroll 1
        for (int p = 0; p < 32768; p += ops) {
          const uint32_t w = p >> 14, c = (p >> 13) & 1, off = w * 8192 + (p & 8191);
          mbar_wait(bar_ofull + (t & 1) * 16 + w * 8, t >> 1);
          if (elect_one()) {
            bulk_store(g_act + (uint32_t)(rb * 80 + 16 + (cj * 4 + t) * 2 + c) * UNIT + off, base + unit_of(QT, 2 * t + c) + off, ops);
            asm volatile("cp.async.bulk.commit_group;" ::: "memory");
            asm volatile("cp.async.bulk.wait_group.read 0;" ::: "memory");
          }
        }
        if (elect_one()) {
          mbar_arrive(t < 3 ? bar_ofree + t * 8 : bar_res);
          asm volatile("cp.async.bulk.wait_group 0;" ::: "memory");
          fence_async();
          red_release(&g_cnt_o[((rb * 4 + t) * 2 + (cj >> 2)) * 32], 2);
        }
        if (t) {
          wait_counter(&g_cnt_o[(rb * 8 + 2 * t + (cj & 1)) * 32], target);
          if (t & 1) wait_counter(&g_cnt_o[(rb * 8 + (t == 1 ? cj & 1 : 7 - (cj & 1))) * 32], target);
          if (elect_one()) mbar_arrive(t == 1 ? bar_ofree + 24 : bar_cnt + t * 8 - 16);
        }
      }
      PROF(2, lane == 0, 27);
      const uint32_t tag = epoch % 3 + 1;
      const uint32_t* inbox = g_cand + (b >> CSH) % CR * 512 + (lane & 15) * CS;
      mbar_wait(bar_ring + 16, 0);
      uint32_t c0 = ld_relaxed(inbox), n = 0;
#define CAND_STEP(cv)                                                                                        \
      {                                                                                                      \
        const bool valid = (cv & 3u) == tag, all = __all_sync(0xffffffffu, valid);                           \
        const uint32_t best = __reduce_max_sync(0xffffffffu, valid ? cv : 0u);                               \
        const uint32_t blk = __ffs(__ballot_sync(0xffffffffu, cv == best)) - 1;                              \
        if (best) sts2(par + PAR_CONST + 56, best, (blk << 7 | (~best >> 2 & 127)) | (all ? 0x1800 : 0x800)); \
        if (all) break;                                                                                      \
        cv = ld_relaxed(inbox);                                                                              \
      }
      while (true) { CAND_STEP(c0) watchdog(n); }
    } else {
      const int t2 = tid - 320;
      if (late && warp == 10) {
        mbar_wait(bar_hx, 0);
        if (elect_one()) {
          tma2d(stage, &maps.wm, (b >> 1) * 32, rank * 512, bar_hw);
          tma2d(stage + 16384, &maps.wm, (b >> 1) * 32, rank * 512 + 256, bar_hw);
        }
      }
      {
        const uint32_t tag = epoch % 3 + 1;
        mbar_wait(bar_hx + 8, 0);
        mbar_wait(bar_hw, 0);
        __nanosleep(late ? OSL2 : OSL);
        {
          const uint32_t t7 = (warp & 1) * 64 + (lane >> 4) * 32 + 16 + (lane & 15);
          const uint32_t* pm = g_modp + ((cj * 128 + t7 * 4) & (DM - 1));
          uint4 m0, m1, m2, m3;
          uint32_t n = 0;
          do {
            m0 = ld_relaxed4(pm); m1 = ld_relaxed4(pm + 2 * DM); m2 = ld_relaxed4(pm + DM); m3 = ld_relaxed4(pm + 3 * DM);
            watchdog(n);
          } while (!__all_sync(0xffffffffu, tag_ok(m0, tag) && tag_ok(m1, tag) && tag_ok(m2, tag) && tag_ok(m3, tag)));
          write_table(par, false, t7, m0, m1);
          write_table(par, true, t7, m2, m3);
          mbar_arrive(bar_mod2);
        }
      }
      mbar_wait(bar_hpub + (warp & 1) * 8, 0);
      PROF(1, t2 == 0, 24);
#pragma unroll 1
      for (int c = 0; c < 8; c++) {
        const uint32_t off = (warp & 1) * UNIT + c * 2048 + lane * 16;
        uint8_t* dst = g_act + (uint32_t)(rb * 80 + cj * 2) * UNIT + off;
        const uint4 v0 = lds4(stage + off), v1 = lds4(stage + off + 512), v2 = lds4(stage + off + 1024), v3 = lds4(stage + off + 1536);
        stg4(dst, v0); stg4(dst + 512, v1); stg4(dst + 1024, v2); stg4(dst + 1536, v3);
      }
      __syncwarp();
      PROF(1, t2 == 0, 15);
      if (lane == 0) {
        mbar_arrive(bar_pread);
        red_release(&g_cnt_h[rb * 32 + cj * 2 + (warp & 1)], 1);
        PROF(1, t2 == 0, 25);
        prefetch_map(&maps.wg); prefetch_map(&maps.wu); prefetch_map(&maps.wd); prefetch_map(&maps.out);
      }
      __syncwarp();
      if (b < NFFN) {
        mbar_wait(bar_go2, 0);
        const __nv_bfloat16* pg = ((b & 1) ? P.w_up : P.w_gate) + (b >> 1) * 64 + (size_t)t2 * FF;
        const __nv_bfloat16* pd = P.w_down + (size_t)b * 32768 + t2 * 64;
        PROF(2, t2 == 0, 13);
#pragma unroll 1
        for (int i = 0; i < WN; i += WB) {
          uint32_t v[WB];
#pragma unroll
          for (int u = 0; u < WB; u++) {
            const int k = i + u;
            asm volatile("ld.global.cg.L2::128B.u32 %0, [%1];" : "=r"(v[u]) : "l"(k < 16 ? pg + (size_t)k * 64 * FF : pd + (k - 16) * 4096));
          }
#pragma unroll
          for (int u = 1; u < WB; u++) v[0] ^= v[u];
          sts1(par + PAR_SINK + t2 * 4, v[0]);
        }
        PROF(2, t2 == 0, 14);
      }
      const uint32_t tag = epoch % 3 + 1;
      mbar_wait(bar_go, 0);
      bar_sync(4, 64);
      if (warp == 10) {
        const uint32_t* src = g_mod + 2 * DM + cj * 128 + lane * 4;
        const uint2 wr = *reinterpret_cast<const uint2*>(P.w_r + cj * 128 + lane * 4);
        uint4 vga, vsb, vcb, vgb;
        uint32_t n = 0;
        do {
          vga = ld_relaxed4(src); vsb = ld_relaxed4(src + DM); vcb = ld_relaxed4(src + 2 * DM); vgb = ld_relaxed4(src + 3 * DM);
          watchdog(n);
        } while (!__all_sync(0xffffffffu, tag_ok(vga, tag) && tag_ok(vsb, tag) && tag_ok(vcb, tag) && tag_ok(vgb, tag)));
        const float c0 = rbf(1.f + bf_hi(vcb.x)), c1 = rbf(1.f + bf_hi(vcb.y)), c2 = rbf(1.f + bf_hi(vcb.z)), c3 = rbf(1.f + bf_hi(vcb.w));
        const float a0 = c0 * bf_lo(wr.x), a1 = c1 * bf_hi(wr.x), a2 = c2 * bf_lo(wr.y), a3 = c3 * bf_hi(wr.y);
        const uint32_t h0 = pack_bf(a0, a1), h1 = pack_bf(a2, a3);
        const uint32_t t1 = par + PAR_T1 + (lane >> 2) * 64 + (lane & 1) * 32 + (lane & 2) * 2;
        sts1(t1, h0); sts1(t1 + 8, pack_bf(a0 - bf_lo(h0), a1 - bf_hi(h0)));
        sts1(t1 + 16, h1); sts1(t1 + 24, pack_bf(a2 - bf_lo(h1), a3 - bf_hi(h1)));
        const uint32_t tg = par + PAR_SINK + (lane >> 3) * 64 + (lane & 1) * 32 + (lane & 6) * 2;
        sts1(tg, __byte_perm(vga.x, vga.y, 0x7632)); sts1(tg + 16, __byte_perm(vga.z, vga.w, 0x7632));
        sts4(par + PAR_T2 + lane * 32, make_uint4(pack_bf(c0, c1), __byte_perm(vsb.x, vsb.y, 0x7632), __byte_perm(vgb.x, vgb.y, 0x7632), __byte_perm(vga.x, vga.y, 0x7632)));
        sts4(par + PAR_T2 + lane * 32 + 16, make_uint4(pack_bf(c2, c3), __byte_perm(vsb.z, vsb.w, 0x7632), __byte_perm(vgb.z, vgb.w, 0x7632), __byte_perm(vga.z, vga.w, 0x7632)));
      } else {
        const uint4 g = poll4((lane & 8) ? g_mod + 8 - (lane & 1) * 4 : g_mod + 5 * DM + (b >> 4) * 128 + (lane & 7) * 16 + (b & 12), tag);
        sts1(par + PAR_CONST + 60, 0);
        if (lane < 8) sts1(par + PAR_CONST + 16 + lane * 4, (b & 2) ? ((b & 1) ? g.w : g.z) : ((b & 1) ? g.y : g.x));
        else if (lane < 10) sts2(par + PAR_CONST + (lane - 8) * 8, __float_as_uint(untag_sum(g.x, g.y) + untag_sum(g.z, g.w)), epoch);
      }
      __syncwarp();
#pragma unroll 1
      for (int q = 0; q < 32; q++) {
        st_b128(g_xch + ((size_t)b * 8 * 256 + q * 64 + t2) * 4, (epoch & 1) << 16, 0, 0, 0);
        __nanosleep(RSL);
      }
      for (int q = 0; q < 2; q++) st_relaxed4(g_stats + (((rb * 8 + q * 4 + (t2 >> 4)) * 8 + cj) * 16 + (t2 & 15)) * 4, 0, 0, 0, 0);
      if (b < NFFN)
        for (int q = 0; q < 2; q++) st_relaxed4(ypart_slot(b, q * 64 + t2), 0, 0, 0, 0);
      st_relaxed4(g_row + rb * 2 * DM + (t2 >> 5) * DM + cj * 128 + (t2 & 31) * 4, 0, 0, 0, 0);
      __threadfence();
      mbar_arrive(bar_par);
      mbar_wait(bar_gate, 0);
      uint32_t have = 0, n = 0;
      while (true) {
        const uint32_t st = lds1(par + PAR_CONST + 60) >> 7;
        if ((st & 31) != have) {
          const uint32_t* hsrc = g_row + (st & 15) * 2 * DM + t2 * 4;
          uint4 hv[4];
          bool ok = true;
#pragma unroll
          for (int i = 0; i < 4; i++) hv[i] = ld_pairs(hsrc + i * 256);
#pragma unroll
          for (int i = 0; i < 4; i++) {
            sts2(base + ((FT_G >> i * 4) & 15) * UNIT + (warp & 1) * 8192 + 256 + lane * 8, hv[i].x, hv[i].z);
            ok = ok && hv[i].y == tag && hv[i].w == tag;
          }
          have = __all_sync(0xffffffffu, ok) ? st & 31 : 0;
        }
        if ((st ^ have) == 32) break;
        watchdog(n);
      }
      mbar_arrive(bar_sel);
    }
    __syncwarp();
    cluster_arrive();
    {
      const uint32_t tag = epoch % 3 + 1, t3 = tid - 256;
      mbar_wait(bar_win, 0);
      uint2 win = lds2(par + PAR_CONST + 56);
      win.y &= 0x7ff;
      const uint32_t* fsrc = g_row + (win.y >> 7) * 2 * DM + (b >> 4) * 128 + (t3 & 7) * 16 + (b & 6) * 2 + ((b >> 2) & 2);
      const uint32_t* ysrc = ypart_slot(min(t3, NFFN - 1), b);
      uint2 fh = ld_pair(fsrc), fx = ld_pair(fsrc + DM);
      uint4 ya = ld_b128(ysrc);
      const float rwin = __uint_as_float(((int)win.x < 0 ? win.x & 0x7fffffffu : ~win.x) & ~0x1ffu);
      const float rs = rbf(rcp(1.f + __expf(-rbf(rwin))));
      uint32_t n = 0;
      while (__any_sync(0xffffffffu, fh.y != tag || fx.y != tag)) { fh = ld_pair(fsrc); fx = ld_pair(fsrc + DM); watchdog(n); }
      while (true) {
        const bool miss = ((ya.x & 1) | (ya.y & 1) << 1) != tag;
        if (!__any_sync(0xffffffffu, miss)) break;
        if (miss) ya = ld_b128(ysrc);
        watchdog(n);
      }
      PROF(8, t3 == 0, 5);
      float y[8] = {bf_lo(ya.x & ~1u), bf_hi(ya.x), bf_lo(ya.y & ~1u), bf_hi(ya.y), bf_lo(ya.z), bf_hi(ya.z), bf_lo(ya.w), bf_hi(ya.w)};
#pragma unroll
      for (int h = 4; h > 0; h >>= 1) {
        const bool up = lane & (h * 2);
#pragma unroll
        for (int e = 0; e < h; e++) y[e] = (up ? y[e + h] : y[e]) + __shfl_xor_sync(0xffffffffu, up ? y[e] : y[e + h], h * 2);
      }
      y[0] += __shfl_xor_sync(0xffffffffu, y[0], 1);
      if (!(lane & 1)) sts1(par + PAR_RED + 64 + t3 * 2, __float_as_uint(y[0]));
      bar_sync(4, 128);
      if (t3 < 8) {
        float y0 = 0.f;
#pragma unroll
        for (int w7 = 0; w7 < 7; w7++) y0 += __uint_as_float(lds1(par + PAR_RED + 64 + w7 * 32 + t3 * 4));
        const uint32_t gv = lds1(par + PAR_CONST + 16 + t3 * 4);
        const uint32_t upd = hmul2(pack_bf(y0, y0), pack_bf(rs, rs));
        const uint32_t r = hadd2(fx.x, hmul2(__byte_perm(gv, gv, 0x3232), hadd2(fh.x, upd)));
        reinterpret_cast<uint16_t*>(P.out)[(size_t)win.y * DM + (b >> 4) * 128 + t3 * 16 + (b & 15)] = (b & 1) ? r >> 16 : r;
        if (b == 0 && t3 == 0) st_relaxed(&g_epoch, epoch + 1);
      }
      PROF(31, t3 == 0, 36);
    }
    cluster_wait();
  } else {
    const int wg = warp >> 2;

    uint32_t tag;
    {
      uint32_t* const pmod = g_modp + rank * 2 * DM + (b >> 1) * 32 + lane;
      uint32_t* const pln = g_ln1 + (rb * 128 + cj * 16 + warp) * 4;
      uint32_t sc[8];
#pragma unroll
      for (int k = 0; k < 8; k++) sc[k] = ldg_nc1(P.c + rank * 512 + warp * 64 + k * 8 + (lane & 3) * 2);
      const uint32_t epoch = ld_relaxed(&g_epoch);
      if (warp == 0) st_relaxed(pmod, 0);
      if (lane == 0) { st_b128(pln, 0, 0, 0, 0); st_b128(pln + 32, 0, 0, 0, 0); }
      asm volatile("setmaxnreg.inc.sync.aligned.u32 232;");
      bar_sync(1, 320);
#pragma unroll
      for (int k = 0; k < 8; k++) sc[k] = pack_bf(silu_f(bf_lo(sc[k])), silu_f(bf_hi(sc[k])));
      keep(sc);
      tag = epoch % 3 + 1;
#pragma unroll
      for (int part = 0; part < 4; part++) {
        if (!(part & 1)) {
          const uint32_t xa = base + (2 + part / 2) * GST_BYTES + warp * 2048 + lane * 16;
          mbar_wait(bar_hx + part * 4, 0);
          float s0 = 0.f, s1 = 0.f, q0 = 0.f, q1 = 0.f;
#pragma unroll
          for (int q = 0; q < 4; q++) {
            const uint4 xv = lds4(xa + q * 512);
            const uint32_t u[4] = {xv.x, xv.y, xv.z, xv.w};
#pragma unroll
            for (int e = 0; e < 4; e++) { const float lo = bf_lo(u[e]), hi = bf_hi(u[e]); s0 += lo; s1 += hi; q0 += lo * lo; q1 += hi * hi; }
          }
          s0 += s1; q0 += q1;
#pragma unroll
          for (int o = 16; o > 0; o >>= 1) { s0 += __shfl_xor_sync(0xffffffffu, s0, o); q0 += __shfl_xor_sync(0xffffffffu, q0, o); }
          const float mean = s0 * (1.f / DM);
          float mb, sd;
          ln_scalars(mean, fmaxf(q0 * (1.f / DM) - mean * mean, 0.f), mb, sd);
          uint32_t ih, il;
          split_inv(sd, ih, il);
          if (lane == 0) st_b128(pln + part * 16, pack_bf(mb, mb), ih, il, tag);
          PROF(1, tid == 0 && part == 2, 4);
        } else if (late == (part == 3)) {
          const uint32_t fr = (lane & 7) + (lane >> 4) * 8, tq = lane & 3;
          const uint32_t wa = stage + warp * 4096 + fr * 64 + ((((lane >> 3) & 1) ^ ((fr >> 1) & 3)) << 4);
          float d0[4] = {0.f, 0.f, 0.f, 0.f}, d1[4] = {0.f, 0.f, 0.f, 0.f};
          mbar_wait(bar_hw, 0);
#pragma unroll
          for (int ks = 0; ks < 4; ks++) {
            uint32_t w[8];
            ldmatrix4t(wa + ks * 1024, w[0], w[1], w[2], w[3]);
            ldmatrix4t((wa ^ 32) + ks * 1024, w[4], w[5], w[6], w[7]);
            mma16816(d0, w[0], w[1], w[2], w[3], sc[2 * ks], sc[2 * ks + 1]);
            mma16816(d1, w[4], w[5], w[6], w[7], sc[2 * ks], sc[2 * ks + 1]);
          }
          sts1(base + 2 * GST_BYTES + warp * 2048 + (tq * 8 + (lane >> 2)) * 4, __float_as_uint((tq & 2) ? ((tq & 1) ? d1[2] : d1[0]) : ((tq & 1) ? d0[2] : d0[0])));
          bar_sync(1, 256);
          if (warp == 0) {
            float s = 0.f;
#pragma unroll
            for (int w8 = 0; w8 < 8; w8++) s += __uint_as_float(lds1(base + 2 * GST_BYTES + w8 * 2048 + lane * 4));
            st_relaxed(pmod, (__float_as_uint(s) & ~3u) | tag);
          }
          PROF(1, tid == 0, 3);
        }
      }
      cluster_wait();
      if (wg == 1) bar_arrive(2, 256);
    }

    float f0 = 0.f, f1 = 0.f;
    const uint32_t rempty = lane < 2 ? mapa(bempty, lane & 1) : 0;
    constexpr uint32_t GE = NSLOT * 8 + 32;
    float o[64], s[64];
#pragma unroll 1
    for (int ps = 0; ps < 3; ps++) {
      {
        const uint32_t xt = ps == 1 ? XT1 : XT2, wt = ps == 1 ? WT1 : WT2;
        const int nst = ps == 2 ? 28 : 14;
        if (ps == 0) {
          float ga[64], gb[64];
#pragma unroll
          for (int i = 0; i < 64; i++) { ga[i] = 0.f; gb[i] = 0.f; }
          uint32_t a[2][16];
          const uint32_t l = fresh_lane();
          uint32_t fa[4];
#pragma unroll
          for (int kk = 0; kk < 4; kk++) fa[kk] = (base + wg * 8192 + frag_offset(warp)) ^ (kk * 32);
          const uint32_t mt = par + (l & 3) * 16;
          auto fetch = [&](int i, uint32_t (&f)[16], uint32_t z) {
            mbar_wait(xfull + (i & 3) * 8, i >> 2);
#pragma unroll
            for (int kk = 0; kk < 4; kk++) ldmatrix4(fa[kk] + (i & 3) * GST_BYTES + z, f[4 * kk], f[4 * kk + 1], f[4 * kk + 2], f[4 * kk + 3]);
          };
          const bool oddw = warp & 2;
          uint4 r0, r1;
          {
            const uint32_t t7 = (warp & 1) * 64 + (l >> 4) * 32 + (l & 15);
            const uint32_t* pm = g_modp + wg * DM + ((cj * 128 + t7 * 4) & (DM - 1));
            const uint32_t* pr = g_ln1 + (rb * 128 + warp * 16 + (l >> 2)) * 4;
            uint4 m0 = make_uint4(tag, tag, tag, tag), m1 = m0;
            if (!oddw) { m0 = ld_relaxed4(pm); m1 = ld_relaxed4(pm + 2 * DM); }
            r0 = ld_b128(pr); r1 = ld_b128(pr + 32);
            fetch(0, a[0], 0); fetch(1, a[1], 0);
            uint32_t n = 0;
            bool written = false;
#pragma unroll 1
            while (true) {
              uint32_t miss;
              asm volatile("{ .reg .pred p0, p1, p2, p3; .reg .b32 t, u;\n"
                           "lop3.b32 t, %1, %2, %19, 0x7e; lop3.b32 u, %3, %4, %19, 0x7e; or.b32 t, t, u; and.b32 t, t, 3; setp.ne.u32 p0, t, 0;\n"
                           "lop3.b32 t, %5, %6, %19, 0x7e; lop3.b32 u, %7, %8, %19, 0x7e; or.b32 t, t, u; and.b32 t, t, 3; setp.ne.u32 p1, t, 0;\n"
                           "setp.ne.u32 p2, %12, %19; setp.ne.u32 p3, %16, %19;\n"
                           "@p0 ld.relaxed.gpu.global.v4.u32 {%1, %2, %3, %4}, [%17];\n"
                           "@p1 ld.relaxed.gpu.global.v4.u32 {%5, %6, %7, %8}, [%17 + 8192];\n"
                           "@p2 ld.relaxed.gpu.global.v4.u32 {%9, %10, %11, %12}, [%18];\n"
                           "@p3 ld.relaxed.gpu.global.v4.u32 {%13, %14, %15, %16}, [%18 + 128];\n"
                           "or.pred p0, p0, p1; or.pred p2, p2, p3; vote.sync.any.pred p0, p0, 0xffffffff; vote.sync.any.pred p2, p2, 0xffffffff;\n"
                           "selp.u32 t, 1, 0, p0; selp.u32 u, 2, 0, p2; or.b32 %0, t, u; }"
                           : "=r"(miss), "+r"(m0.x), "+r"(m0.y), "+r"(m0.z), "+r"(m0.w), "+r"(m1.x), "+r"(m1.y), "+r"(m1.z), "+r"(m1.w),
                             "+r"(r0.x), "+r"(r0.y), "+r"(r0.z), "+r"(r0.w), "+r"(r1.x), "+r"(r1.y), "+r"(r1.z), "+r"(r1.w)
                           : "l"(pm), "l"(pr), "r"(tag) : "memory");
              if (!(miss & 1) && !written) {
                written = true;
                if (!oddw) write_table(par, wg, t7, m0, m1);
                mbar_arrive(bar_mod);
              }
              if (!miss) break;
              watchdog(n);
            }
          }
          const uint32_t zero = r0.w ^ tag;
          auto normalize = [&](uint32_t (&f)[16]) {
#pragma unroll
            for (int k = 0; k < 16; k += 2) { f[k] = ln_norm(f[k], r0.x, r0.y, r0.z); f[k + 1] = ln_norm(f[k + 1], r1.x, r1.y, r1.z); }
          };
          auto modulate = [&](int i, uint32_t (&f)[16]) {
#pragma unroll
            for (int kk = 0; kk < 4; kk++) {
              const uint4 m = lds4(mt + slice_of(i) * 256 + kk * 64);
              f[4 * kk] = hfma2(f[4 * kk], m.x, m.z); f[4 * kk + 1] = hfma2(f[4 * kk + 1], m.x, m.z);
              f[4 * kk + 2] = hfma2(f[4 * kk + 2], m.y, m.w); f[4 * kk + 3] = hfma2(f[4 * kk + 3], m.y, m.w);
            }
            keep(f);
            mbar_arrive_pred(xempty + (i & 3) * 8, l == 0);
          };
          auto publish = [&](int u, uint32_t (&f)[16]) {
#pragma unroll
            for (int kk = 0; kk < 4; kk++) stmatrix4(fa[kk] + OFF_STAGE + u * UNIT, f[4 * kk], f[4 * kk + 1], f[4 * kk + 2], f[4 * kk + 3]);
            __syncwarp();
            mbar_arrive_pred(bar_hpub + u * 8, l == 0);
          };
          auto multiply = [&](int i, uint32_t (&f)[16]) {
            mbar_wait(gfull + (i & 3) * 8, i >> 2);
            const uint64_t db = make_desc(base + (i & 3) * GST_BYTES + UNIT, 8192, 1024);
            wg_fence();
#pragma unroll
            for (int kk = 0; kk < 4; kk++) mma256_rs(ga, gb, f[4 * kk], f[4 * kk + 1], f[4 * kk + 2], f[4 * kk + 3], db + kk * 128);
            wg_commit();
          };
          auto next = [&](int i, uint32_t (&f)[16]) {
            wg_wait<1>();
            mbar_arrive_cl(rempty, GE + ((i + 2) & 3) * 8);
            uint32_t z = zero;
#pragma unroll
            for (int k = 0; k < 16; k += 2) asm volatile("lop3.b32 %0, %1, %2, %0, 0xA8;" : "+r"(z) : "r"(f[k]), "r"(f[k + 1]));
            fetch(i, f, z);
            normalize(f);
            if (i == 2) { keep(f); mbar_wait(bar_mod2, 0); }
            modulate(i, f); multiply(i, f);
          };
          normalize(a[0]); normalize(a[1]);
          keep(a[0]); keep(a[1]);
          mbar_wait(bar_mod, 0);
          PROF(1, tid == 0, 2);
          modulate(0, a[0]); multiply(0, a[0]); publish(0, a[0]);
          modulate(1, a[1]); multiply(1, a[1]);
#pragma unroll 1
          for (int i = 2; i < NRS; i += 2) {
            next(i, a[0]);
            if (i == 2) publish(1, a[0]);
            next(i + 1, a[1]);
          }
          wg_wait<1>();
          mbar_arrive_cl(rempty, GE + ((NRS + 2) & 3) * 8);
#pragma unroll 1
          for (int i = NRS; i < 14; i++) {
            mbar_wait(xfull + (i & 3) * 8, (i >> 2) & 1);
            mbar_wait(gfull + (i & 3) * 8, (i >> 2) & 1);
            const uint32_t xa = base + (i & 3) * GST_BYTES;
            const uint64_t da = make_desc(xa + wg * 8192, 16, 1024), db = make_desc(xa + UNIT, 8192, 1024);
            if (i == 13) bar_sync(2 + wg, 256);
            wg_fence();
#pragma unroll
            for (int kk = 0; kk < 4; kk++) mma256_ss(ga, gb, da + kk * 2, db + kk * 128, 1);
            wg_commit();
            if (i == 13) bar_arrive(3 - wg, 256);
            wg_wait<1>();
            uint32_t z = zero;
#pragma unroll
            for (int k = 0; k < 16; k += 2) asm volatile("lop3.b32 %0, %1, %2, %0, 0xA8;" : "+r"(z) : "r"(a[1][k]), "r"(a[1][k + 1]));
            mbar_arrive_cl(rempty, GE + ((i + 3) & 3) * 8 + z);
            mbar_arrive_pred(xempty + ((i + 3) & 3) * 8, l == 0 && i != NRS);
          }
          mbar_wait(xfull + 16, 1);
          wg_wait<0>();
          keep(ga); keep(gb);
#pragma unroll
          for (int i = 0; i < 64; i++) {
            asm volatile("mov.b32 %0, %1;" : "=f"(s[i]) : "f"(ga[i]));
            asm volatile("mov.b32 %0, %1;" : "=f"(o[i]) : "f"(gb[i]));
          }
        } else {
          float ga[64], gb[64];
#pragma unroll
          for (int i = 0; i < 64; i++) {
            asm volatile("mov.b32 %0, %1;" : "=f"(ga[i]) : "f"(s[i]));
            asm volatile("mov.b32 %0, %1;" : "=f"(gb[i]) : "f"(o[i]));
          }
#pragma unroll 1
          for (int i = 0; i < nst; i++) {
            mbar_wait(gfull + (i & 3) * 8, (i >> 2) & 1);
            const uint64_t da = make_desc(base + unit_of(xt, i & 3) + wg * 8192, 16, 1024), db = make_desc(base + unit_of(wt, i & 3), 8192, 1024);
            if (i == nst - 1) bar_sync(2 + wg, 256);
            wg_fence();
#pragma unroll
            for (int kk = 0; kk < 4; kk++) mma256_ss(ga, gb, da + kk * 2, db + kk * 128, kk ? 1 : i);
            wg_commit();
            if (i == nst - 1) bar_arrive(3 - wg, 256);
            wg_wait<1>();
            mbar_arrive_cl(rempty, GE + ((i + 3) & 3) * 8, i != 0);
            PROF(4, tid == 0 && (i & 3) == 0, 40 + (ps - 1) * 4 + i / 4);
          }
          wg_wait<0>();
          keep(ga); keep(gb);
#pragma unroll
          for (int i = 0; i < 64; i++) {
            asm volatile("mov.b32 %0, %1;" : "=f"(s[i]) : "f"(ga[i]));
            asm volatile("mov.b32 %0, %1;" : "=f"(o[i]) : "f"(gb[i]));
          }
        }
        mbar_arrive_cl(rempty, GE + (ps == 2 ? 24 : 8));
        if (ps == 2) break;
      }
      const uint32_t qw = base + wg * 8192, qt = QT >> (16 * ps), at = ps ? AT1 : AT0;
      {
        const uint32_t wt = ps ? WT1 : WT0;
        const uint64_t da0 = make_desc(qw + unit_of(qt, 2), 16, 1024), da1 = make_desc(qw + unit_of(qt, 3), 16, 1024);
        const uint64_t db0 = make_desc(base + unit_of(wt, 2), 8192, 1024), db1 = make_desc(base + unit_of(wt, 3), 8192, 1024);
        mbar_wait(gfull + 16, 1);
        bar_sync(2 + wg, 256);
        wg_fence();
#pragma unroll
        for (int kk = 0; kk < 4; kk++) mma_ss<1>(s, da0 + kk * 2, db0 + kk * 128, 1);
        wg_commit();
        mbar_wait(xfull + 24, 1);
        mbar_wait(gfull + 24, 1);
        wg_fence();
#pragma unroll
        for (int kk = 0; kk < 4; kk++) mma_ss<1>(s, da1 + kk * 2, db1 + kk * 128, 1);
        wg_commit();
        bar_arrive(3 - wg, 256);
        mbar_wait(ps == 0 ? bar_pread : bar_ofree + 8, 0);
        wg_wait<0>();
        keep(s);
        PROF(2, tid == 0, 8 + ps * 8);
        uint32_t q[32];
        pack_p(s, q);
#pragma unroll
        for (int i = 0; i < 4; i++) stmatrix4((qw + unit_of(qt, 0) + frag_offset(warp)) ^ (i << 5), q[4 * i], q[4 * i + 1], q[4 * i + 2], q[4 * i + 3]);
        keep(q);
        bar_sync(2 + wg, 256);
        wg_fence();
#pragma unroll
        for (int kk = 0; kk < 8; kk++) mma_ss<1>(o, (kk < 4 ? da0 : da1) + (kk & 3) * 2, (kk < 4 ? db0 : db1) + UNIT / 16 + (kk & 3) * 128, 1);
        wg_commit();
        mbar_wait(bfull, 0);
        wg_fence();
        const uint64_t dk = make_desc(base + unit_of(at, 0), 16, 1024);
#pragma unroll
        for (int kk = 0; kk < 8; kk++) mma_rs<0>(s, q[4 * kk], q[4 * kk + 1], q[4 * kk + 2], q[4 * kk + 3], dk + (kk >> 2) * 1024 + (kk & 3) * 2, kk != 0);
        wg_commit();
        bar_arrive(3 - wg, 256);
#pragma unroll
        for (int i = 4; i < 8; i++) stmatrix4((qw + unit_of(qt, 1) + frag_offset(warp)) ^ ((i & 3) << 5), q[4 * i], q[4 * i + 1], q[4 * i + 2], q[4 * i + 3]);
        wg_wait<1>();
        keep(o);
        mbar_arrive_cl(rempty, GE + 16);
        mbar_arrive_cl(rempty, GE + 24);
        store_chunk<0>(o, qw + unit_of(qt, 2) + frag_offset(warp));
        store_chunk<1>(o, qw + unit_of(qt, 3) + frag_offset(warp));
        wg_wait<0>();
        keep(s);
        mbar_arrive_cl(rempty, 0);
      }
      PROF(4, tid == 0 && ps == 1, 61);
      float l0 = 0.f, l1 = 0.f;
      auto step = [&](auto odd_c, const int j, uint32_t (&pw)[32], uint32_t (&pr)[32]) {
        constexpr bool ODD = decltype(odd_c)::value;
        const bool first = !ODD && (j & 2) == 0, last = ODD && j == 7;
        const uint32_t ph = (j >> 1) & 1;
        float i0, i1, a0, a1;
        const bool so = !ODD && j == 4;
        if (so) { i0 = inv_quad_sum(l0); i1 = inv_quad_sum(l1); l0 = 0.f; l1 = 0.f; }
        bool redo = !ODD && (j | ps) == 0;
        while (true) {
          if (redo) {
            float m0 = fmaxf(s[0], s[1]), m1 = fmaxf(s[2], s[3]);
#pragma unroll
            for (int i = 1; i < 16; i++) { m0 = fmaxf(m0, fmaxf(s[4 * i], s[4 * i + 1])); m1 = fmaxf(m1, fmaxf(s[4 * i + 2], s[4 * i + 3])); }
            m0 = fmaxf(m0, __shfl_xor_sync(0xffffffffu, m0, 1)); m1 = fmaxf(m1, __shfl_xor_sync(0xffffffffu, m1, 1));
            m0 = fmaxf(m0, __shfl_xor_sync(0xffffffffu, m0, 2)); m1 = fmaxf(m1, __shfl_xor_sync(0xffffffffu, m1, 2));
            m0 *= SCL2; m1 *= SCL2;
            if (!first) {
              m0 = fmaxf(m0, f0); m1 = fmaxf(m1, f1);
              const float c0 = ex2(f0 - m0), c1 = ex2(f1 - m1);
              l0 *= c0; l1 *= c1;
              wg_wait<0>();
              keep(o);
#pragma unroll
              for (int i = 0; i < 16; i++) { o[4 * i] *= c0; o[4 * i + 1] *= c0; o[4 * i + 2] *= c1; o[4 * i + 3] *= c1; }
            }
            f0 = m0; f1 = m1;
          }
          float b0 = 0.f, b1 = 0.f;
          a0 = 0.f; a1 = 0.f;
#pragma unroll
          for (int i = 0; i < 16; i++) {
            const float e0 = ex2(fmaf(s[4 * i], SCL2, -f0)), e1 = ex2(fmaf(s[4 * i + 1], SCL2, -f0));
            const float e2 = ex2(fmaf(s[4 * i + 2], SCL2, -f1)), e3 = ex2(fmaf(s[4 * i + 3], SCL2, -f1));
            a0 += e0; b0 += e1; a1 += e2; b1 += e3;
            pw[2 * i] = pack_bf(e0, e1); pw[2 * i + 1] = pack_bf(e2, e3);
            if (i == VREL) {
#pragma unroll
              for (int k = 0; k < 2 * VREL + 2; k++) asm volatile("" : "+r"(pw[k])::"memory");
              mbar_wait(bar_mod, 0);
              wg_wait<0>();
              mbar_arrive_cl(rempty, ODD ? 16 : 0, !redo && (ODD || j));
#pragma unroll
              for (int k = 4 * VREL + 4; k < 64; k++) asm volatile("" : "+f"(s[k])::"memory");
            }
          }
          a0 += b0; a1 += b1;
          if (redo) break;
          redo = __any_sync(0xffffffffu, !(a0 + a1 < 0x1p90f) || (!ODD && fminf(a0, a1) < (first ? 0x1p-90f : 0.f)));
          if (!redo) break;
        }
        l0 += a0; l1 += a1;
        keep(pw);
        keep(o);
        if (so) store_chunk<0>(o, i0, i1, qw + unit_of(qt, 0) + frag_offset(warp));
        keep(o);
        if (j == (ODD ? 5 : 0)) { fence_async_smem(); if (ODD) mbar_arrive(bar_ofull + wg * 8); }
        mbar_wait(bfull + (ODD ? 24 : 8), ph);
        bar_sync(2 + wg, 256);
        if (!last) {
          const uint32_t qn = qt >> (j >= 3 ? 8 : 0);
          wg_fence();
          issue_qk(s, qw + unit_of(qn, 0), qw + unit_of(qn, 1), base + unit_of(at, ODD ? 3 : 1));
          wg_commit();
          mbar_wait(bfull + (ODD ? 0 : 16), ODD ? ph ^ 1 : ph);
        }
        if (so) { store_chunk<1>(o, i0, i1, qw + unit_of(qt, 1) + frag_offset(warp)); keep(o); }
        wg_fence();
        issue_pv(o, pw, base + unit_of(at, ODD ? (last ? 3 : 0) : 2), !first);
        wg_commit();
        bar_arrive(3 - wg, 256);
        wg_wait<1>();
        keep(s);
        mbar_arrive_cl(rempty, ODD ? 24 : 8, !last);
        PROF(4, tid == 0 && ps == 1, 51 + j);
      };
      uint32_t pa[32], pb[32];
#pragma unroll 1
      for (int j = 0; j < 8; j += 2) {
        step(std::false_type{}, j, pa, pb);
        step(std::true_type{}, j + 1, pb, pa);
      }
      {
        const float i0 = inv_quad_sum(l0), i1 = inv_quad_sum(l1);
        wg_wait<0>();
        keep(o);
        mbar_arrive_cl(rempty, 24);
        store_chunk<0>(o, i0, i1, qw + unit_of(qt, 2) + frag_offset(warp));
        store_chunk<1>(o, i0, i1, qw + unit_of(qt, 3) + frag_offset(warp));
        fence_async_smem();
        mbar_arrive(bar_ofull + 16 + wg * 8);
      }
      PROF(2, tid == 0, 10 + ps * 8);
    }

    const int ln = fresh_lane(), g = ln >> 2, tq = ln & 3, ct = warp * 32 + ln;
    const bool lane0 = ln == 0;
    const int lrow0 = warp * 16 + g;
    const uint32_t res = base + OFF_RES, trow = res + wg * 8192 + frag_offset(warp);
    uint32_t xr[32];
    uint4 sv[4], own;
    uint32_t* const sg = g_stats + (rb * 8 + warp) * 512 + g * 4;
    uint32_t* sp[4];
#pragma unroll
    for (int k = 0; k < 4; k++) sp[k] = sg + (tq & 1) * 32 + (((tq >> 1) ^ (cj >> 2)) * 4 + (k ^ (cj & 3))) * 64;
    {
      const uint64_t da = make_desc(base + wg * 8192, 16, 1024), db = make_desc(base, 8192, 1024);
      constexpr int U = UNIT / 16;
#define HALF_STAGE(acc, xu, wu) _Pragma("unroll") for (int kk = 0; kk < 4; kk++) mma_ss<1>(acc, da + (xu) * U + kk * 2, db + (wu) * U + kk * 128, 1)
      PROF(10, ct == PT, 19); STAMP(0);
      cluster_arrive();
      mbar_wait(gfull, 1);
      mbar_wait(gfull + 8, 1);
      bar_sync(2 + wg, 256);
      wg_fence();
      HALF_STAGE(o, 7, 1);
      HALF_STAGE(o, 8, 3);
      wg_commit();
      STAMP(16);
      mbar_wait(gfull + 16, 1);
      STAMP(17);
      wg_fence();
      HALF_STAGE(o, 6, 11);
      wg_commit();
      bar_arrive(3 - wg, 256);
      mbar_wait(bar_par, 0);
      uint32_t* xo = g_xch + ((size_t)b * 8 * 256 + ct) * 4;
      const uint32_t* xi = g_xch + ((size_t)(b ^ 2) * 8 * 256 + ct) * 4;
      const uint32_t par1 = (~lds1(par + PAR_CONST + 4) & 1) << 16;
      wg_wait<1>();
      mbar_arrive_pred(bar_rel, lane0);
      wg_wait<0>();
      keep(o);
      mbar_arrive_pred(bar_ring, lane0);
      PROF(8, ct == PT, 20); STAMP(1);
#define SEND(i) st_b128(xo + (i) * 1024, (pack_bf(o[8 * (i)], o[8 * (i) + 1]) & ~0x10000u) | par1, pack_bf(o[8 * (i) + 2], o[8 * (i) + 3]), \
                        pack_bf(o[8 * (i) + 4], o[8 * (i) + 5]), pack_bf(o[8 * (i) + 6], o[8 * (i) + 7]))
#pragma unroll
      for (int i = 0; i < NS1; i++) SEND(i);
      PROF(8, ct == PT, 21); STAMP(2);
      bar_sync(2 + wg, 256);
      wg_fence();
      HALF_STAGE(s, 7, 0);
      HALF_STAGE(s, 8, 2);
      HALF_STAGE(s, 6, 10);
      wg_commit();
      bar_arrive(3 - wg, 256);
      STAMP(18);
      mbar_wait(gfull + 24, 1);
#pragma unroll
      for (int i = NS1; i < 8; i++) SEND(i);
      uint4 v[8];
      STAMP(19);
      mbar_wait(bar_xres, 0);
      wg_wait<0>();
      mbar_arrive_pred(bar_ring + 8, lane0);
      bar_sync(2 + wg, 256);
      STAMP(20);
#pragma unroll
      for (int i = 0; i < LD2; i++) v[i] = ld_b128(xi + i * 1024);
      mbar_wait(bar_xres, 0);
      wg_fence();
      HALF_STAGE(s, 9, 4);
      wg_commit();
      mbar_wait(bar_rx, 0);
      wg_fence();
      HALF_STAGE(s, 1, 5);
      wg_commit();
      bar_arrive(3 - wg, 256);
      STAMP(21);
#pragma unroll
      for (int i = LD2; i < 8; i++) v[i] = ld_b128(xi + i * 1024);
      mbar_wait(bar_xres, 0);
      wg_wait<0>();
      keep(s);
      mbar_arrive_pred(bar_ring + 16, lane0);
      PROF(10, ct == PT, 23); STAMP(4);
#pragma unroll
      for (int i = 0; i < 16; i += 2) ldmatrix4((trow ^ ((i & 7) << 4)) + (i >> 3) * 16384, xr[2 * i], xr[2 * i + 1], xr[2 * i + 2], xr[2 * i + 3]);
      uint32_t ga[16];
      uint4 bw[8];
#pragma unroll
      for (int i = 0; i < 8; i++) {
        if (!(i & 1)) {
          const uint4 t = lds4(par + PAR_SINK + i * 32 + tq * 16);
          ga[2 * i] = t.x; ga[2 * i + 1] = t.y; ga[2 * i + 2] = t.z; ga[2 * i + 3] = t.w;
        }
        bw[i] = lds4(par + PAR_T1 + i * 64 + tq * 16);
        if (!(g & 1)) { bw[i].x = 0x3f803f80u; bw[i].y = 0x3f803f80u; }
      }
      uint32_t pk[32];
      pack_p(s, pk);
      const uint32_t par2 = (~lds1(par + PAR_CONST + 12) & 1) << 16;
      {
        uint32_t n = 0, miss;
        do {
          miss = 0;
#pragma unroll
          for (int i = 0; i < 8; i++) miss |= v[i].x ^ par2;
          miss = __any_sync(0xffffffffu, miss & 0x10000u);
          if (miss) {
#pragma unroll
            for (int i = 0; i < 8; i++)
              asm volatile("{ .reg .pred p; .reg .b32 t; xor.b32 t, %0, %5; and.b32 t, t, 0x10000; setp.ne.u32 p, t, 0;\n"
                           "@p ld.relaxed.gpu.global.v4.u32 {%0, %1, %2, %3}, [%4]; }"
                           : "+r"(v[i].x), "+r"(v[i].y), "+r"(v[i].z), "+r"(v[i].w) : "l"(xi + i * 1024), "r"(par1) : "memory");
          }
          watchdog(n);
        } while (miss);
      }
      PROF(8, ct == PT, 22); STAMP(3);
      float ds[4] = {0.f, 0.f, 0.f, 0.f}, dl[4] = {0.f, 0.f, 0.f, 0.f}, q0[4] = {0.f, 0.f, 0.f, 0.f}, q1[4] = {0.f, 0.f, 0.f, 0.f};
#pragma unroll
      for (int i = 0; i < 8; i++) {
        const uint32_t u0 = hfma2(ga[2 * i], hadd2(pk[4 * i], v[i].x & ~0x10000u), xr[4 * i]);
        const uint32_t u1 = hfma2(ga[2 * i], hadd2(pk[4 * i + 1], v[i].y), xr[4 * i + 1]);
        const uint32_t u2 = hfma2(ga[2 * i + 1], hadd2(pk[4 * i + 2], v[i].z), xr[4 * i + 2]);
        const uint32_t u3 = hfma2(ga[2 * i + 1], hadd2(pk[4 * i + 3], v[i].w), xr[4 * i + 3]);
        xr[4 * i] = u0; xr[4 * i + 1] = u1; xr[4 * i + 2] = u2; xr[4 * i + 3] = u3;
        mma16816(ds, u0, u1, u2, u3, bw[i].x, bw[i].y);
        mma16816(dl, u0, u1, u2, u3, bw[i].z, bw[i].w);
        mma16816(q0, u0, u1, u2, u3, u0, u2);
        mma16816(q1, u0, u1, u2, u3, u1, u3);
      }
      const float sqa = (g & 1) ? q0[1] : q0[0], sqb = (g & 1) ? q1[3] : q1[2], dta = ds[1] + dl[1], dtb = ds[3] + dl[3];
      if (tq == (g >> 1)) {
        st_b128(sg + cj * 64, __float_as_uint(ds[0]), __float_as_uint(sqa), __float_as_uint(dta), tag);
        st_b128(sg + cj * 64 + 32, __float_as_uint(ds[2]), __float_as_uint(sqb), __float_as_uint(dtb), tag);
      }
#pragma unroll
      for (int k = 0; k < 4; k++) sv[k] = ld_b128(sp[k]);
      mbar_wait(bar_xres, 0);
      const float sqc = __shfl_sync(0xffffffffu, sqa, g * 4 + (g >> 1)), sqd = __shfl_sync(0xffffffffu, sqb, g * 4 + (g >> 1));
      own = (tq & 1) ? make_uint4(__float_as_uint(ds[2]), __float_as_uint(sqd), __float_as_uint(dtb), tag)
                     : make_uint4(__float_as_uint(ds[0]), __float_as_uint(sqc), __float_as_uint(dta), tag);
    }
    PROF(8, ct == PT, 29); STAMP(5);
    uint32_t mm, ih, il;
    float rbest;
    uint32_t wf[128];
    const uint32_t frow = (ln & 7) + (ln >> 4) * 8;
    const uint32_t wfo = base + (warp & 1) * 8192 + frow * 64 + ((((ln >> 3) & 1) ^ ((frow >> 1) & 3)) << 4);
#define LOAD_WF(m) _Pragma("unroll") for (int f = 0; f < 16; f++) {                                                   \
      const int r = ((f >> 1) * 4 + (m) * 2 + (f & 1)) * 4;                                                           \
      ldmatrix4t(((wfo + unit_of((m) ? FT_U : FT_G, warp >> 1)) ^ ((f & 1) * 32)) + (f >> 1) * 1024, wf[r], wf[r + 1], wf[r + 2], wf[r + 3]); \
    }
    bool early;
    {
#pragma unroll
      for (int i = 0; i < 16; i += 2) stmatrix4((trow ^ ((i & 7) << 4)) + (i >> 3) * 16384, xr[2 * i], xr[2 * i + 1], xr[2 * i + 2], xr[2 * i + 3]);
      const uint4 cst = lds4(par + PAR_CONST);
      const float A1 = __uint_as_float(cst.x), A2 = __uint_as_float(cst.z);
      uint32_t n = 0;
      early = false;
#pragma unroll 1
      while (true) {
        if (!early && (b >= NFFN || __all_sync(0xffffffffu, mbar_test(bar_box + (warp >> 1) * 8, 0)))) {
          early = true;
          LOAD_WF(0);
          __syncwarp();
          mbar_arrive_pred(bar_gate, lane0);
        }
        uint32_t miss;
        asm volatile("{ .reg .pred p0, p1, p2, p3; .reg .b64 u, v; .reg .b128 w;\n"
                     "setp.ge.u32 p0, %22, 2; setp.ne.and.u32 p0, %4, %21, p0; setp.ne.u32 p1, %8, %21; setp.ne.u32 p2, %12, %21; setp.ne.u32 p3, %16, %21;\n"
                     "@p0 ld.relaxed.gpu.global.v4.u32 {%1, %2, %3, %4}, [%17];\n"
                     "@p1 ld.relaxed.gpu.global.v4.u32 {%5, %6, %7, %8}, [%18];\n"
                     "@p2 ld.relaxed.gpu.global.v4.u32 {%9, %10, %11, %12}, [%19];\n"
                     "@p3 ld.relaxed.gpu.global.v4.u32 {%13, %14, %15, %16}, [%20];\n"
                     "or.pred p0, p0, p1; or.pred p2, p2, p3; or.pred p0, p0, p2; vote.sync.any.pred p0, p0, 0xffffffff; selp.u32 %0, 1, 0, p0; }"
                     : "=r"(miss), "+r"(sv[0].x), "+r"(sv[0].y), "+r"(sv[0].z), "+r"(sv[0].w), "+r"(sv[1].x), "+r"(sv[1].y), "+r"(sv[1].z), "+r"(sv[1].w),
                       "+r"(sv[2].x), "+r"(sv[2].y), "+r"(sv[2].z), "+r"(sv[2].w), "+r"(sv[3].x), "+r"(sv[3].y), "+r"(sv[3].z), "+r"(sv[3].w)
                     : "l"(sp[0]), "l"(sp[1]), "l"(sp[2]), "l"(sp[3]), "r"(tag), "r"(tq) : "memory");
        if (!miss) break;
        watchdog(n);
      }
      const uint4 v0 = tq < 2 ? own : sv[0], v1 = sv[1], v2 = sv[2], v3 = sv[3];
      PROF(8, ct == PT, 30); STAMP(6);
      float su = (__uint_as_float(v0.x) + __uint_as_float(v1.x)) + (__uint_as_float(v2.x) + __uint_as_float(v3.x));
      float sq = (__uint_as_float(v0.y) + __uint_as_float(v1.y)) + (__uint_as_float(v2.y) + __uint_as_float(v3.y));
      float dt = (__uint_as_float(v0.z) + __uint_as_float(v1.z)) + (__uint_as_float(v2.z) + __uint_as_float(v3.z));
      su += __shfl_xor_sync(0xffffffffu, su, 2); sq += __shfl_xor_sync(0xffffffffu, sq, 2); dt += __shfl_xor_sync(0xffffffffu, dt, 2);
      const float m = su * (1.f / DM);
      float mb, sd;
      ln_scalars(m, fmaxf(sq * (1.f / DM) - m * m, 0.f), mb, sd);
      const float inv = rcp(sd);
      rbest = (dt - mb * A1) * inv + A2;
      mm = pack_bf(mb, mb);
      ih = pack_bf(inv, inv);
      const float lo = inv - bf_lo(ih);
      il = pack_bf(lo, lo);
    }
    int ibest;
    {
      const uint32_t bits = __float_as_uint(rbest);
      const uint32_t key = (((int)bits < 0 ? ~bits : bits | 0x80000000u) & ~0x1ffu) | ((127 - lrow0 - (tq & 1) * 8) << 2) | tag;
      sts1(par + PAR_RED + warp * 4, __reduce_max_sync(0xffffffffu, key));
      PROF(8, ct == PT, 38); STAMP(7);
      bar_sync(1, 256);
      const uint4 ka = lds4(par + PAR_RED), kb = lds4(par + PAR_RED + 16);
      const uint32_t k2 = max(max(max(ka.x, ka.y), max(ka.z, ka.w)), max(max(kb.x, kb.y), max(kb.z, kb.w)));
      if (ct < CR && cj == 0) st_relaxed(g_cand + ct * 512 + rb * CS, k2);
      ibest = 127 - ((k2 >> 2) & 127);
    }
    PROF(8, ct == PT, 39); STAMP(8);
    if ((ibest >> 4) == warp) {
      const int src = (ibest & 7) * 4 + ((ibest >> 3) & 1), ch = g * 2;
      const uint32_t cm = __shfl_sync(0xffffffffu, mm, src), ch_ = __shfl_sync(0xffffffffu, ih, src), cl = __shfl_sync(0xffffffffu, il, src);
      const uint32_t xa = res + (ch >> 3) * 16384 + ibest * 128 + (((ch & 7) ^ (ibest & 7)) << 4) + tq * 4;
      const uint32_t x0 = lds1(xa), x1 = lds1(xa ^ 16);
      const uint2 p0 = lds2(par + PAR_T2 + ch * 64 + tq * 16), p1 = lds2(par + PAR_T2 + ch * 64 + 64 + tq * 16);
      uint32_t* dst = g_row + rb * 2 * DM + cj * 128 + ln * 4;
      st_pairs(dst, ln_mod(x0, cm, ch_, cl, p0.x, p0.y), ln_mod(x1, cm, ch_, cl, p1.x, p1.y), tag);
      st_pairs(dst + DM, x0, x1, tag);
      __syncwarp();
    }
    PROF(8, ct == PT, 37); STAMP(9);
    uint32_t wd[64];
    const uint32_t wda = base + unit_of(FT_D, warp >> 1) + (warp & 1) * 8192 + frow * 128 + ((((ln >> 3) & 1) ^ (ln & 7)) << 4);
#define LOAD_WD(f) ldmatrix4t((wda ^ ((((f) >> 1) & 3) * 32)) + ((f) >> 3) * 4096 + ((f) & 1) * 2048, wd[4 * (f)], wd[4 * (f) + 1], wd[4 * (f) + 2], wd[4 * (f) + 3])
    if (!early) {
      if (b < NFFN) mbar_wait(bar_box + (warp >> 1) * 8, 0);
      LOAD_WF(0);
      __syncwarp();
      mbar_arrive_pred(bar_gate, lane0);
    }
    if (b < NFFN) {
      const uint32_t own = base + unit_of(FT_G, warp >> 1) + (warp & 1) * 8192;
      mbar_wait(bar_box + (4 + (warp >> 1)) * 8, 0);
      LOAD_WF(1);
      uint32_t* const ydst = ypart_slot(b, warp * 16 + (tq & 1) * 8 + g);
      PROF(8, ct == PT, 31); STAMP(10);
      bool wdok;
      {
        uint32_t n = 0;
        while (!(wdok = __all_sync(0xffffffffu, mbar_test(bar_box + (8 + (warp >> 1)) * 8, 0))) && !__all_sync(0xffffffffu, mbar_test(bar_sel, 0))) watchdog(n);
      }
      if (wdok) {
#pragma unroll
        for (int f = 0; f < 16; f++) LOAD_WD(f);
      }
      STAMP(11);
      mbar_wait(bar_sel, 0);
      PROF(8, ct == PT, 33); STAMP(12);
      float d[8][4];
#pragma unroll
      for (int i = 0; i < 4; i++) { d[i][0] = 0.f; d[i][1] = 0.f; d[i][2] = 0.f; d[i][3] = 0.f; }
#pragma unroll
      for (int ks = 0; ks < 8; ks++) {
        const uint2 hb = lds2(own + 256 + ks * 32 + tq * 8);
#pragma unroll
        for (int mt = 0; mt < 4; mt++) {
          const int r = ks * 16 + mt * 4;
          mma16816(d[mt], wf[r], wf[r + 1], wf[r + 2], wf[r + 3], hb.x, hb.y);
        }
      }
      sts2(own + (tq * 8 + g) * 8, __float_as_uint((tq & 2) ? ((tq & 1) ? d[1][2] : d[1][0]) : ((tq & 1) ? d[0][2] : d[0][0])),
           __float_as_uint((tq & 2) ? ((tq & 1) ? d[3][2] : d[3][0]) : ((tq & 1) ? d[2][2] : d[2][0])));
      bar_sync(1, 256);
      uint32_t ab[4];
      {
        float G = 0.f, U = 0.f;
        uint2 pv[8];
#pragma unroll
        for (int w8 = 0; w8 < 8; w8++) pv[w8] = lds2(base + ln * 8 + ((FT_G >> (w8 >> 1) * 4) & 15) * UNIT + (w8 & 1) * 8192);
#pragma unroll
        for (int w8 = 0; w8 < 8; w8 += 2) {
          G += __uint_as_float(pv[w8].x) + __uint_as_float(pv[w8 + 1].x);
          U += __uint_as_float(pv[w8].y) + __uint_as_float(pv[w8 + 1].y);
        }
        const float act = rbf(silu_f(rbf(G))) * rbf(U);
        const uint32_t pk = pack_bf(act, __shfl_down_sync(0xffffffffu, act, 1));
#pragma unroll
        for (int i = 0; i < 4; i++) ab[i] = __shfl_sync(0xffffffffu, pk, i * 8 + tq * 2);
      }
      if (!wdok) {
        mbar_wait(bar_box + (8 + (warp >> 1)) * 8, 0);
#pragma unroll
        for (int f = 0; f < 16; f++) LOAD_WD(f);
      }
      PROF(8, ct == PT, 34); STAMP(13);
#pragma unroll
      for (int mt = 0; mt < 8; mt++) {
        d[mt][0] = 0.f; d[mt][1] = 0.f; d[mt][2] = 0.f; d[mt][3] = 0.f;
        mma16816(d[mt], wd[mt * 8], wd[mt * 8 + 1], wd[mt * 8 + 2], wd[mt * 8 + 3], ab[0], ab[1]);
        mma16816(d[mt], wd[mt * 8 + 4], wd[mt * 8 + 5], wd[mt * 8 + 6], wd[mt * 8 + 7], ab[2], ab[3]);
      }
      uint32_t yw[4];
#pragma unroll
      for (int i = 0; i < 4; i++) yw[i] = (tq & 1) ? pack_bf(d[2 * i][2], d[2 * i + 1][2]) : pack_bf(d[2 * i][0], d[2 * i + 1][0]);
      if (tq < 2) st_b128(ydst, (yw[0] & ~1u) | (tag & 1), (yw[1] & ~1u) | (tag >> 1), yw[2], yw[3]);
      PROF(8, ct == PT, 35); STAMP(14);
    }
    mbar_wait(bar_sel, 0);
    mbar_arrive_pred(bar_win, ct == 0);
    const int iwin = lds1(par + PAR_CONST + 60) & 0x7ff;
    const bool cand = (iwin >> 4) == rb * 8 + warp;
    {
      const uint32_t mm0 = __shfl_sync(0xffffffffu, mm, ln & ~1), mm1 = __shfl_sync(0xffffffffu, mm, ln | 1);
      const uint32_t ih0 = __shfl_sync(0xffffffffu, ih, ln & ~1), ih1 = __shfl_sync(0xffffffffu, ih, ln | 1);
      const uint32_t il0 = __shfl_sync(0xffffffffu, il, ln & ~1), il1 = __shfl_sync(0xffffffffu, il, ln | 1);
#pragma unroll 1
      for (int hf = 0; hf < 2; hf++) {
        uint32_t x[16];
#pragma unroll
        for (int i = 0; i < 8; i += 2) ldmatrix4((trow ^ (i << 4)) + hf * 16384, x[2 * i], x[2 * i + 1], x[2 * i + 2], x[2 * i + 3]);
#pragma unroll
        for (int i = 0; i < 8; i++) {
          const uint4 pv = lds4(par + PAR_T2 + (hf * 8 + i) * 64 + tq * 16);
          x[2 * i] = hfma2(hfma2(ln_norm(x[2 * i], mm0, ih0, il0), pv.x, pv.y), pv.z, x[2 * i]);
          x[2 * i + 1] = hfma2(hfma2(ln_norm(x[2 * i + 1], mm1, ih1, il1), pv.x, pv.y), pv.z, x[2 * i + 1]);
        }
#pragma unroll
        for (int i = 0; i < 8; i += 2) stmatrix4((trow ^ (i << 4)) + hf * 16384, x[2 * i], x[2 * i + 1], x[2 * i + 2], x[2 * i + 3]);
        if (!cand) fence_async_smem();
        __syncwarp();
        if (!cand && elect_one()) {
          tma2d_store(&maps.out, res + hf * 16384 + warp * 2048, cj * 128 + hf * 64, rb * 128 + warp * 16);
          asm volatile("cp.async.bulk.commit_group;" ::: "memory");
        }
      }
    }
    if (cand) {
      const int wrow0 = warp * 16;
#pragma unroll 2
      for (int p = 0; p < 8; p++) {
        const int row = 2 * p + (ln >> 4), ch = ln & 15;
        const uint4 v = lds4(res + (ch >> 3) * 16384 + (wrow0 + row) * 128 + (((ch & 7) ^ (row & 7)) << 4));
        if (rb * 128 + wrow0 + row != iwin) *reinterpret_cast<uint4*>(P.out + (size_t)(rb * 128 + wrow0 + row) * DM + cj * 128 + ch * 8) = v;
      }
    }
    asm volatile("cp.async.bulk.wait_group.read 0;" ::: "memory");
    PROF(8, ct == PT, 11); STAMP(15);
    cluster_wait();
  }
}

typedef CUresult (*EncodeFn)(CUtensorMap*, CUtensorMapDataType, cuuint32_t, void*, const cuuint64_t*, const cuuint64_t*,
                             const cuuint32_t*, const cuuint32_t*, CUtensorMapInterleave, CUtensorMapSwizzle,
                             CUtensorMapL2promotion, CUtensorMapFloatOOBfill);

void map2d(EncodeFn enc, CUtensorMap* m, const void* p, uint64_t rows, uint64_t cols, uint32_t brows) {
  cuuint64_t dims[2] = {cols, rows}, strides[1] = {cols * 2};
  cuuint32_t box[2] = {64, brows}, es[2] = {1, 1};
  enc(m, CU_TENSOR_MAP_DATA_TYPE_BFLOAT16, 2, const_cast<void*>(p), dims, strides, box, es, CU_TENSOR_MAP_INTERLEAVE_NONE,
      CU_TENSOR_MAP_SWIZZLE_128B, CU_TENSOR_MAP_L2_PROMOTION_L2_256B, CU_TENSOR_MAP_FLOAT_OOB_FILL_NONE);
}
void map2d_narrow(EncodeFn enc, CUtensorMap* m, const void* p, uint64_t rows, uint64_t cols, uint32_t brows) {
  cuuint64_t dims[2] = {cols, rows}, strides[1] = {cols * 2};
  cuuint32_t box[2] = {32, brows}, es[2] = {1, 1};
  enc(m, CU_TENSOR_MAP_DATA_TYPE_BFLOAT16, 2, const_cast<void*>(p), dims, strides, box, es, CU_TENSOR_MAP_INTERLEAVE_NONE,
      CU_TENSOR_MAP_SWIZZLE_64B, CU_TENSOR_MAP_L2_PROMOTION_L2_64B, CU_TENSOR_MAP_FLOAT_OOB_FILL_NONE);
}
void map3d(EncodeFn enc, CUtensorMap* m, const void* p, uint64_t rows, uint64_t cols, uint32_t brows, uint32_t nch) {
  cuuint64_t dims[3] = {64, rows, cols / 64}, strides[2] = {cols * 2, 128};
  cuuint32_t box[3] = {64, brows, nch}, es[3] = {1, 1, 1};
  enc(m, CU_TENSOR_MAP_DATA_TYPE_BFLOAT16, 3, const_cast<void*>(p), dims, strides, box, es, CU_TENSOR_MAP_INTERLEAVE_NONE,
      CU_TENSOR_MAP_SWIZZLE_128B, CU_TENSOR_MAP_L2_PROMOTION_L2_256B, CU_TENSOR_MAP_FLOAT_OOB_FILL_NONE);
}

}

extern "C" void kernel_launch(void* const* d_in, const int* in_sizes, int n_in, void* d_out, int out_size) {
  (void)in_sizes; (void)n_in; (void)out_size;
  static EncodeFn enc = nullptr;
  if (!enc) {
    void* fn = nullptr;
    cudaDriverEntryPointQueryResult st;
    cudaGetDriverEntryPoint("cuTensorMapEncodeTiled", &fn, cudaEnableDefault, &st);
    enc = (EncodeFn)fn;
    cudaFuncSetAttribute(fused_kernel, cudaFuncAttributeMaxDynamicSharedMemorySize, SMEM_BYTES);
  }
  Maps maps;
  map2d(enc, &maps.x, d_in[0], SEQ, DM, 128);
  map2d(enc, &maps.out, d_out, SEQ, DM, 16);
  map3d(enc, &maps.wq, d_in[3], DM, NQ, 64, 2);
  map3d(enc, &maps.k, d_in[1], 4 * SK, 128, 128, 1);
  map3d(enc, &maps.v, d_in[2], 4 * SK, 128, 128, 1);
  map3d(enc, &maps.wo, d_in[4], NQ, DM, 64, 2);
  map2d_narrow(enc, &maps.wg, d_in[7], DM, FF, 256);
  map2d_narrow(enc, &maps.wu, d_in[8], DM, FF, 256);
  map3d(enc, &maps.wd, d_in[9], FF, DM, 32, 4);
  map2d_narrow(enc, &maps.wm, d_in[11], DM, NMOD, 256);
  Ptrs p;
  p.x = (const __nv_bfloat16*)d_in[0];
  p.w_r = (const __nv_bfloat16*)d_in[6];
  p.w_gate = (const __nv_bfloat16*)d_in[7];
  p.w_up = (const __nv_bfloat16*)d_in[8];
  p.w_down = (const __nv_bfloat16*)d_in[9];
  p.c = (const __nv_bfloat16*)d_in[10];
  p.w_mod = (const __nv_bfloat16*)d_in[11];
  p.out = (__nv_bfloat16*)d_out;
  fused_kernel<<<NMAIN + NHELP, 384, SMEM_BYTES>>>(maps, p);
}
```

```cpp
#include <cuda_runtime.h>
#include <cuda_bf16.h>
#include <cuda.h>
#include <stdint.h>
#include <type_traits>

#define HD 2
#define HDX 2
#define NRS 8
#define OSL 900
#define OSL2 400
#define RSL 40
#define VREL 5
#define OPS 8192
#define ODS1 5
#define ODS 7
#define PG0 15
#define WB 2
#define WN 20
#define HU 32
#define RES0 17
#define RES1 20
#define GOST 20
#define NS1 5
#define LD2 4
#define FPACE0 2
#define FPACE 3
#define CR 8
#define CS 8

namespace {

constexpr int SEQ = 2048, DM = 1024, NQ = 4096, SK = 2048, WIN = 512, FF = 3584, NMOD = 6144;
constexpr int NMAIN = 128, NHELP = 4, NFFN = 112;
constexpr int NSLOT = 4, SLOT_BYTES = 32768, UNIT = 16384, GST_BYTES = 3 * UNIT;
constexpr uint32_t XT1 = 0xDCBA, XT2 = 0x9687;
constexpr uint32_t WT0 = 0xA741, WT1 = 0x7420, WT2 = 0x4A20;
constexpr uint32_t AT0 = WT1, AT1 = WT2;
constexpr uint32_t QT = 0xDC9696DC;
constexpr int OFF_STAGE = 12 * UNIT;
constexpr uint32_t FT_G = 0x07B3, FT_U = 0xA628, FT_D = 0x5149;
constexpr int OFF_RES = 12 * UNIT;
constexpr int OFF_PAR = 14 * UNIT;
constexpr int OFF_BAR = OFF_PAR + 2528;
constexpr int SMEM_BYTES = OFF_BAR + 544;
static_assert(SMEM_BYTES <= 232448, "smem");

constexpr int PAR_T1 = 0;
constexpr int PAR_T2 = 512;
constexpr int PAR_CONST = 1536;
constexpr int PAR_RED = 1600;
constexpr int PAR_SINK = 2176;

struct Maps {
  CUtensorMap x, wq, k, v, wo, wg, wu, wd, wm, out;
};
struct Ptrs {
  const __nv_bfloat16 *x, *w_r, *c, *w_mod, *w_gate, *w_up, *w_down;
  __nv_bfloat16* out;
};

__device__ __align__(1024) uint8_t g_act[16 * 80 * UNIT];
__device__ __align__(128) uint32_t g_mod[NMOD];
__device__ __align__(128) uint32_t g_modp[2 * 2 * DM];
__device__ __align__(128) uint32_t g_ln1[SEQ * 4];
__device__ __align__(128) uint32_t g_cnt_h[16 * 32];
__device__ __align__(128) uint32_t g_cnt_o[128 * 32];
__device__ __align__(128) uint32_t g_xch[NMAIN * 8 * 256 * 4];
__device__ __align__(128) uint32_t g_stats[8 * SEQ * 4];
__device__ __align__(128) uint32_t g_cand[CR * 512];
__device__ __align__(128) uint32_t g_row[16 * 2 * DM];
__device__ __align__(128) uint32_t g_ypart[NMAIN * NFFN * 4];
__device__ __forceinline__ uint32_t* ypart_slot(int writer, int reader) { return g_ypart + (writer * NMAIN + reader) * 4; }
__device__ uint32_t g_epoch;

__device__ __forceinline__ uint32_t fresh_lane() { uint32_t l; asm volatile("mov.u32 %0, %%laneid;" : "=r"(l)); return l; }
__device__ __forceinline__ uint32_t frag_offset(int warp) {
  const uint32_t l = fresh_lane();
  return ((warp & 3) * 16 + (l & 15)) * 128 + (((l >> 4) ^ (l & 7)) << 4);
}
__device__ __forceinline__ bool elect_one() {
  uint32_t p;
  asm volatile("{ .reg .pred q; elect.sync _|q, 0xffffffff; selp.u32 %0, 1, 0, q; }" : "=r"(p));
  return p;
}
__device__ __forceinline__ uint32_t smem_u32(const void* p) { return (uint32_t)__cvta_generic_to_shared(p); }
__device__ __forceinline__ void mbar_init(uint32_t bar, uint32_t cnt) {
  asm volatile("mbarrier.init.shared::cta.b64 [%0], %1;" ::"r"(bar), "r"(cnt) : "memory");
}
__device__ __forceinline__ void mbar_expect_tx(uint32_t bar, uint32_t bytes) {
  asm volatile("mbarrier.arrive.expect_tx.shared::cta.b64 _, [%0], %1;" ::"r"(bar), "r"(bytes) : "memory");
}
__device__ __forceinline__ void mbar_arrive(uint32_t bar) {
  asm volatile("mbarrier.arrive.shared::cta.b64 _, [%0];" ::"r"(bar) : "memory");
}
__device__ __forceinline__ void mbar_arrive_pred(uint32_t bar, bool p) {
  asm volatile("{ .reg .pred p; setp.ne.b32 p, %1, 0; @p mbarrier.arrive.shared::cta.b64 _, [%0]; }" ::"r"(bar), "r"((int)p) : "memory");
}
__device__ __forceinline__ void mbar_arrive_cl(uint32_t bar, uint32_t off, bool p = true) {
  asm volatile("{ .reg .pred p, q; .reg .b32 a; setp.ne.b32 q, %2, 0; setp.ne.and.b32 p, %0, 0, q; add.u32 a, %0, %1; @p mbarrier.arrive.shared::cluster.b64 _, [a]; }"
               ::"r"(bar), "r"(off), "r"((int)p) : "memory");
}
__device__ __forceinline__ uint32_t mapa(uint32_t addr, uint32_t cta) {
  uint32_t r; asm("mapa.shared::cluster.u32 %0, %1, %2;" : "=r"(r) : "r"(addr), "r"(cta)); return r;
}
__device__ __forceinline__ void cluster_arrive() { asm volatile("barrier.cluster.arrive.relaxed.aligned;" ::: "memory"); }
__device__ __forceinline__ void cluster_wait() { asm volatile("barrier.cluster.wait.aligned;" ::: "memory"); }
__device__ __forceinline__ void watchdog(uint32_t& n) {
}
__device__ __forceinline__ void mbar_wait(uint32_t bar, uint32_t parity) {
  asm volatile("{\n.reg .pred p;\nWAIT_%=:\nmbarrier.try_wait.parity.shared::cta.b64 p, [%0], %1;\n@!p bra WAIT_%=;\n}" ::"r"(bar), "r"(parity) : "memory");
}
__device__ __forceinline__ bool mbar_test(uint32_t bar, uint32_t parity) {
  uint32_t ok;
  asm volatile("{\n.reg .pred p;\nmbarrier.test_wait.parity.shared::cta.b64 p, [%1], %2;\nselp.u32 %0, 1, 0, p;\n}" : "=r"(ok) : "r"(bar), "r"(parity) : "memory");
  return ok;
}
__device__ __forceinline__ uint64_t l2_stream() {
  uint64_t f; asm("createpolicy.fractional.L2::evict_first.b64 %0, 1.0;" : "=l"(f)); return f;
}
__device__ __forceinline__ uint64_t l2_normal() {
  uint64_t f; asm("createpolicy.fractional.L2::evict_normal.b64 %0, 1.0;" : "=l"(f)); return f;
}
__device__ __forceinline__ void tma2d(uint32_t dst, const CUtensorMap* m, int c0, int c1, uint32_t bar) {
  asm volatile("cp.async.bulk.tensor.2d.shared::cluster.global.mbarrier::complete_tx::bytes.L2::cache_hint [%0], [%1, {%3, %4}], [%2], %5;"
               ::"r"(dst), "l"(m), "r"(bar), "r"(c0), "r"(c1), "l"(l2_stream()) : "memory");
}
__device__ __forceinline__ void bulk_load(uint32_t dst, const void* src, uint32_t bytes, uint32_t bar) {
  asm volatile("cp.async.bulk.shared::cluster.global.mbarrier::complete_tx::bytes [%0], [%1], %2, [%3];" ::"r"(dst), "l"(src), "r"(bytes), "r"(bar) : "memory");
}
__device__ __forceinline__ void bulk_load_stream(uint32_t dst, const void* src, uint32_t bytes, uint32_t bar, uint64_t pol = l2_stream()) {
  asm volatile("cp.async.bulk.shared::cluster.global.mbarrier::complete_tx::bytes.L2::cache_hint [%0], [%1], %2, [%3], %4;"
               ::"r"(dst), "l"(src), "r"(bytes), "r"(bar), "l"(pol) : "memory");
}
__device__ __forceinline__ void tma2d_store(const CUtensorMap* m, uint32_t src, int c0, int c1) {
  asm volatile("cp.async.bulk.tensor.2d.global.shared::cta.bulk_group [%0, {%2, %3}], [%1];" ::"l"(m), "r"(src), "r"(c0), "r"(c1) : "memory");
}
__device__ __forceinline__ void bulk_store(void* dst, uint32_t src, uint32_t bytes) {
  asm volatile("cp.async.bulk.global.shared::cta.bulk_group [%0], [%1], %2;" ::"l"(dst), "r"(src), "r"(bytes) : "memory");
}
__device__ __forceinline__ int slice_of(int i) { return i + ((i & 7) == 1) - ((i & 7) == 2); }
__device__ __forceinline__ uint32_t unit_of(uint32_t table, uint32_t i) { return ((table >> (i * 4)) & 15) * UNIT; }
__device__ __forceinline__ void tma3d(uint32_t dst, const CUtensorMap* m, int c0, int c1, int c2, uint32_t bar) {
  asm volatile("cp.async.bulk.tensor.3d.shared::cluster.global.mbarrier::complete_tx::bytes.L2::cache_hint [%0], [%1, {%3, %4, %5}], [%2], %6;"
               ::"r"(dst), "l"(m), "r"(bar), "r"(c0), "r"(c1), "r"(c2), "l"(l2_stream()) : "memory");
}
template <bool STREAM>
__device__ __forceinline__ void tma3d_mc(uint32_t dst, const CUtensorMap* m, int c0, int c1, int c2, uint32_t bar) {
  if (STREAM)
    asm volatile("cp.async.bulk.tensor.3d.shared::cluster.global.mbarrier::complete_tx::bytes.multicast::cluster.L2::cache_hint [%0], [%1, {%3, %4, %5}], [%2], %6, %7;"
                 ::"r"(dst), "l"(m), "r"(bar), "r"(c0), "r"(c1), "r"(c2), "h"((uint16_t)3), "l"(l2_stream()) : "memory");
  else
    asm volatile("cp.async.bulk.tensor.3d.shared::cluster.global.mbarrier::complete_tx::bytes.multicast::cluster [%0], [%1, {%3, %4, %5}], [%2], %6;"
                 ::"r"(dst), "l"(m), "r"(bar), "r"(c0), "r"(c1), "r"(c2), "h"((uint16_t)3) : "memory");
}
__device__ __forceinline__ void prefetch_map(const CUtensorMap* m) {
  asm volatile("prefetch.tensormap [%0];" ::"l"(m) : "memory");
}
__device__ __forceinline__ void fence_async() { asm volatile("fence.proxy.async.global;" ::: "memory"); }
__device__ __forceinline__ void fence_async_smem() { asm volatile("fence.proxy.async.shared::cta;" ::: "memory"); }
__device__ __forceinline__ void bar_sync(int id, int n) { asm volatile("bar.sync %0, %1;" ::"r"(id), "r"(n) : "memory"); }
__device__ __forceinline__ void bar_arrive(int id, int n) { asm volatile("bar.arrive %0, %1;" ::"r"(id), "r"(n) : "memory"); }
__device__ __forceinline__ void wg_fence() { asm volatile("wgmma.fence.sync.aligned;" ::: "memory"); }
__device__ __forceinline__ void wg_commit() { asm volatile("wgmma.commit_group.sync.aligned;" ::: "memory"); }
template <int N> __device__ __forceinline__ void wg_wait() { asm volatile("wgmma.wait_group.sync.aligned %0;" ::"n"(N) : "memory"); }
__device__ __forceinline__ uint64_t make_desc(uint32_t addr, uint32_t lbo, uint32_t sbo) {
  return (uint64_t)((addr & 0x3FFFF) >> 4) | ((uint64_t)(lbo >> 4) << 16) | ((uint64_t)(sbo >> 4) << 32) | (1ull << 62);
}
__device__ __forceinline__ uint32_t ld_relaxed(const uint32_t* p) {
  uint32_t v; asm volatile("ld.relaxed.gpu.global.u32 %0, [%1];" : "=r"(v) : "l"(p) : "memory"); return v;
}
__device__ __forceinline__ uint32_t ld_acquire(const uint32_t* p) {
  uint32_t v; asm volatile("ld.acquire.gpu.global.u32 %0, [%1];" : "=r"(v) : "l"(p) : "memory"); return v;
}
__device__ __forceinline__ uint4 ld_relaxed4(const uint32_t* p) {
  uint4 v; asm volatile("ld.relaxed.gpu.global.v4.u32 {%0,%1,%2,%3}, [%4];" : "=r"(v.x), "=r"(v.y), "=r"(v.z), "=r"(v.w) : "l"(p) : "memory"); return v;
}
__device__ __forceinline__ void st_relaxed(uint32_t* p, uint32_t v) {
  asm volatile("st.relaxed.gpu.global.u32 [%0], %1;" ::"l"(p), "r"(v) : "memory");
}
__device__ __forceinline__ void st_relaxed4(uint32_t* p, uint32_t a, uint32_t b, uint32_t c, uint32_t d) {
  asm volatile("st.relaxed.gpu.global.v4.u32 [%0], {%1,%2,%3,%4};" ::"l"(p), "r"(a), "r"(b), "r"(c), "r"(d) : "memory");
}
__device__ __forceinline__ void st_b128(uint32_t* p, uint32_t a, uint32_t b, uint32_t c, uint32_t d) {
  asm volatile("{ .reg .b64 u, v; .reg .b128 w; mov.b64 u, {%1, %2}; mov.b64 v, {%3, %4}; mov.b128 w, {u, v}; st.relaxed.gpu.global.b128 [%0], w; }"
               ::"l"(p), "r"(a), "r"(b), "r"(c), "r"(d) : "memory");
}
__device__ __forceinline__ uint4 ld_b128(const uint32_t* p) {
  uint4 r;
  asm volatile("{ .reg .b64 u, v; .reg .b128 w; ld.relaxed.gpu.global.b128 w, [%4]; mov.b128 {u, v}, w; mov.b64 {%0, %1}, u; mov.b64 {%2, %3}, v; }"
               : "=r"(r.x), "=r"(r.y), "=r"(r.z), "=r"(r.w) : "l"(p) : "memory");
  return r;
}
__device__ __forceinline__ void st_pairs(uint32_t* p, uint32_t a, uint32_t b, uint32_t tag) {
  asm volatile("{ .reg .b64 u, v; mov.b64 u, {%1, %3}; mov.b64 v, {%2, %3}; st.relaxed.gpu.global.v2.b64 [%0], {u, v}; }"
               ::"l"(p), "r"(a), "r"(b), "r"(tag) : "memory");
}
__device__ __forceinline__ uint4 ld_pairs(const uint32_t* p) {
  uint4 v;
  asm volatile("{ .reg .b64 u, v; ld.relaxed.gpu.global.v2.b64 {u, v}, [%4]; mov.b64 {%0, %1}, u; mov.b64 {%2, %3}, v; }"
               : "=r"(v.x), "=r"(v.y), "=r"(v.z), "=r"(v.w) : "l"(p) : "memory");
  return v;
}
__device__ __forceinline__ uint2 ld_pair(const uint32_t* p) {
  uint2 v;
  asm volatile("{ .reg .b64 u; ld.relaxed.gpu.global.b64 u, [%2]; mov.b64 {%0, %1}, u; }" : "=r"(v.x), "=r"(v.y) : "l"(p) : "memory");
  return v;
}
__device__ __forceinline__ void red_release(uint32_t* p, uint32_t v) {
  asm volatile("red.release.gpu.global.add.u32 [%0], %1;" ::"l"(p), "r"(v) : "memory");
}
__device__ __forceinline__ uint32_t ldg_nc1(const void* p) {
  uint32_t v;
  asm volatile("ld.global.nc.u32 %0, [%1];" : "=r"(v) : "l"(p));
  return v;
}
__device__ __forceinline__ uint4 ldg_nc4(const void* p) {
  uint4 v; asm volatile("ld.global.nc.L1::no_allocate.v4.u32 {%0,%1,%2,%3}, [%4];" : "=r"(v.x), "=r"(v.y), "=r"(v.z), "=r"(v.w) : "l"(p)); return v;
}
__device__ __forceinline__ uint4 ldg_stream4(const void* p) {
  uint4 v;
  asm volatile("ld.global.nc.L1::no_allocate.L2::cache_hint.v4.u32 {%0,%1,%2,%3}, [%4], %5;" : "=r"(v.x), "=r"(v.y), "=r"(v.z), "=r"(v.w) : "l"(p), "l"(l2_stream()));
  return v;
}
__device__ __forceinline__ void stg4(void* p, uint4 v) {
  asm volatile("st.global.v4.u32 [%0], {%1,%2,%3,%4};" ::"l"(p), "r"(v.x), "r"(v.y), "r"(v.z), "r"(v.w) : "memory");
}
__device__ __forceinline__ void wait_counter(const uint32_t* p, uint32_t target) {
  uint32_t n = 0;
  while (__any_sync(0xffffffffu, (int)(ld_acquire(p) - target) < 0)) { watchdog(n); }
}
__device__ __forceinline__ uint32_t tagf(float v, uint32_t tag) { return (__float_as_uint(v) & ~3u) | tag; }
__device__ __forceinline__ bool tag_ok(uint4 v, uint32_t tag) { return (((v.x ^ tag) | (v.y ^ tag) | (v.z ^ tag) | (v.w ^ tag)) & 3u) == 0; }
__device__ __forceinline__ float untag_sum(uint32_t a, uint32_t b) { return __uint_as_float(a & ~3u) + __uint_as_float(b & ~3u); }
__device__ __forceinline__ uint4 poll4(const uint32_t* p, uint32_t tag) {
  uint4 v = ld_relaxed4(p);
  uint32_t n = 0;
  while (!__all_sync(0xffffffffu, tag_ok(v, tag))) { v = ld_relaxed4(p); watchdog(n); }
  return v;
}
__device__ __forceinline__ float bf_lo(uint32_t v) { return __uint_as_float(v << 16); }
__device__ __forceinline__ float bf_hi(uint32_t v) { return __uint_as_float(v & 0xffff0000u); }
__device__ __forceinline__ uint32_t pack_bf(float lo, float hi) {
  uint32_t r; asm("cvt.rn.bf16x2.f32 %0, %1, %2;" : "=r"(r) : "f"(hi), "f"(lo)); return r;
}
__device__ __forceinline__ float rbf(float v) { return __uint_as_float(pack_bf(0.f, v) & 0xffff0000u); }
__device__ __forceinline__ uint32_t hmul2(uint32_t a, uint32_t b) {
  uint32_t r; asm("mul.rn.bf16x2 %0, %1, %2;" : "=r"(r) : "r"(a), "r"(b)); return r;
}
__device__ __forceinline__ uint32_t hadd2(uint32_t a, uint32_t b) {
  uint32_t r; asm("add.rn.bf16x2 %0, %1, %2;" : "=r"(r) : "r"(a), "r"(b)); return r;
}
__device__ __forceinline__ uint32_t hsub2(uint32_t a, uint32_t b) {
  uint32_t r; asm("sub.rn.bf16x2 %0, %1, %2;" : "=r"(r) : "r"(a), "r"(b)); return r;
}
__device__ __forceinline__ float rcp(float x) { float r; asm("rcp.approx.ftz.f32 %0, %1;" : "=f"(r) : "f"(x)); return r; }
__device__ __forceinline__ float ex2(float x) { float r; asm("ex2.approx.ftz.f32 %0, %1;" : "=f"(r) : "f"(x)); return r; }
__device__ __forceinline__ void stmatrix4(uint32_t addr, uint32_t a, uint32_t b, uint32_t c, uint32_t d) {
  asm volatile("stmatrix.sync.aligned.m8n8.x4.shared.b16 [%0], {%1,%2,%3,%4};" ::"r"(addr), "r"(a), "r"(b), "r"(c), "r"(d) : "memory");
}
__device__ __forceinline__ void ldmatrix4(uint32_t addr, uint32_t& a, uint32_t& b, uint32_t& c, uint32_t& d) {
  asm volatile("ldmatrix.sync.aligned.m8n8.x4.shared.b16 {%0,%1,%2,%3}, [%4];" : "=r"(a), "=r"(b), "=r"(c), "=r"(d) : "r"(addr) : "memory");
}
__device__ __forceinline__ void ldmatrix4t(uint32_t addr, uint32_t& a, uint32_t& b, uint32_t& c, uint32_t& d) {
  asm volatile("ldmatrix.sync.aligned.m8n8.x4.trans.shared.b16 {%0,%1,%2,%3}, [%4];" : "=r"(a), "=r"(b), "=r"(c), "=r"(d) : "r"(addr) : "memory");
}
__device__ __forceinline__ void mma16816(float (&d)[4], uint32_t a0, uint32_t a1, uint32_t a2, uint32_t a3, uint32_t b0, uint32_t b1) {
  asm volatile("mma.sync.aligned.m16n8k16.row.col.f32.bf16.bf16.f32 {%0,%1,%2,%3}, {%4,%5,%6,%7}, {%8,%9}, {%0,%1,%2,%3};"
               : "+f"(d[0]), "+f"(d[1]), "+f"(d[2]), "+f"(d[3]) : "r"(a0), "r"(a1), "r"(a2), "r"(a3), "r"(b0), "r"(b1));
}
__device__ __forceinline__ void sts1(uint32_t a, uint32_t v) { asm volatile("st.shared.u32 [%0], %1;" ::"r"(a), "r"(v) : "memory"); }
__device__ __forceinline__ uint4 lds4(uint32_t a) {
  uint4 v; asm volatile("ld.shared.v4.u32 {%0,%1,%2,%3}, [%4];" : "=r"(v.x), "=r"(v.y), "=r"(v.z), "=r"(v.w) : "r"(a) : "memory"); return v;
}
__device__ __forceinline__ uint2 lds2(uint32_t a) {
  uint2 v; asm volatile("ld.shared.v2.u32 {%0,%1}, [%2];" : "=r"(v.x), "=r"(v.y) : "r"(a) : "memory"); return v;
}
__device__ __forceinline__ uint32_t lds1(uint32_t a) {
  uint32_t v; asm volatile("ld.shared.u32 %0, [%1];" : "=r"(v) : "r"(a) : "memory"); return v;
}
__device__ __forceinline__ void sts2(uint32_t a, uint32_t x, uint32_t y) { asm volatile("st.shared.v2.u32 [%0], {%1,%2};" ::"r"(a), "r"(x), "r"(y) : "memory"); }
__device__ __forceinline__ void sts4(uint32_t a, uint4 v) {
  asm volatile("st.shared.v4.u32 [%0], {%1,%2,%3,%4};" ::"r"(a), "r"(v.x), "r"(v.y), "r"(v.z), "r"(v.w) : "memory");
}
__device__ __forceinline__ float silu_f(float v) { return __fdividef(v, 1.f + __expf(-v)); }
__device__ __forceinline__ uint32_t hfma2(uint32_t a, uint32_t b, uint32_t c) {
  uint32_t r; asm("fma.rn.bf16x2 %0, %1, %2, %3;" : "=r"(r) : "r"(a), "r"(b), "r"(c)); return r;
}
__device__ __forceinline__ void split_inv(float sd, uint32_t& ih, uint32_t& il) {
  const float inv = rcp(sd);
  ih = pack_bf(inv, inv);
  const float lo = inv - bf_lo(ih);
  il = pack_bf(lo, lo);
}
__device__ __forceinline__ uint32_t ln_norm(uint32_t x, uint32_t mean2, uint32_t ih, uint32_t il) {
  const uint32_t d = hsub2(x, mean2);
  return hfma2(d, ih, hmul2(d, il));
}
__device__ __forceinline__ uint32_t ln_mod(uint32_t x, uint32_t mean2, uint32_t ih, uint32_t il, uint32_t c1, uint32_t sh) {
  return hadd2(hmul2(ln_norm(x, mean2, ih, il), c1), sh);
}

#define R8(a, i) "+f"(a[i]), "+f"(a[i + 1]), "+f"(a[i + 2]), "+f"(a[i + 3]), "+f"(a[i + 4]), "+f"(a[i + 5]), "+f"(a[i + 6]), "+f"(a[i + 7])
#define D64 "{%0,%1,%2,%3,%4,%5,%6,%7,%8,%9,%10,%11,%12,%13,%14,%15,%16,%17,%18,%19,%20,%21,%22,%23,%24,%25,%26,%27,%28,%29,%30,%31," \
            "%32,%33,%34,%35,%36,%37,%38,%39,%40,%41,%42,%43,%44,%45,%46,%47,%48,%49,%50,%51,%52,%53,%54,%55,%56,%57,%58,%59,%60,%61,%62,%63}"
template <int TB>
__device__ __forceinline__ void mma_ss(float (&d)[64], uint64_t da, uint64_t db, int sc) {
  asm volatile("{\n.reg .pred p;\nsetp.ne.b32 p, %66, 0;\n"
               "wgmma.mma_async.sync.aligned.m64n128k16.f32.bf16.bf16 " D64 ", %64, %65, p, 1, 1, 0, %67;\n}"
               : R8(d, 0), R8(d, 8), R8(d, 16), R8(d, 24), R8(d, 32), R8(d, 40), R8(d, 48), R8(d, 56)
               : "l"(da), "l"(db), "r"(sc), "n"(TB));
}
template <int TB>
__device__ __forceinline__ void mma_rs(float (&d)[64], uint32_t a0, uint32_t a1, uint32_t a2, uint32_t a3, uint64_t db, int sc) {
  asm volatile("{\n.reg .pred p;\nsetp.ne.b32 p, %69, 0;\n"
               "wgmma.mma_async.sync.aligned.m64n128k16.f32.bf16.bf16 " D64 ", {%64,%65,%66,%67}, %68, p, 1, 1, %70;\n}"
               : R8(d, 0), R8(d, 8), R8(d, 16), R8(d, 24), R8(d, 32), R8(d, 40), R8(d, 48), R8(d, 56)
               : "r"(a0), "r"(a1), "r"(a2), "r"(a3), "l"(db), "r"(sc), "n"(TB));
}
#define D128 "{%0,%1,%2,%3,%4,%5,%6,%7,%8,%9,%10,%11,%12,%13,%14,%15,%16,%17,%18,%19,%20,%21,%22,%23,%24,%25,%26,%27,%28,%29,%30,%31," \
             "%32,%33,%34,%35,%36,%37,%38,%39,%40,%41,%42,%43,%44,%45,%46,%47,%48,%49,%50,%51,%52,%53,%54,%55,%56,%57,%58,%59,%60,%61,%62,%63," \
             "%64,%65,%66,%67,%68,%69,%70,%71,%72,%73,%74,%75,%76,%77,%78,%79,%80,%81,%82,%83,%84,%85,%86,%87,%88,%89,%90,%91,%92,%93,%94,%95," \
             "%96,%97,%98,%99,%100,%101,%102,%103,%104,%105,%106,%107,%108,%109,%110,%111,%112,%113,%114,%115,%116,%117,%118,%119,%120,%121,%122,%123,%124,%125,%126,%127}"
#define R128(d, e) R8(d, 0), R8(d, 8), R8(d, 16), R8(d, 24), R8(d, 32), R8(d, 40), R8(d, 48), R8(d, 56), \
                   R8(e, 0), R8(e, 8), R8(e, 16), R8(e, 24), R8(e, 32), R8(e, 40), R8(e, 48), R8(e, 56)
__device__ __forceinline__ void mma256_ss(float (&d)[64], float (&e)[64], uint64_t da, uint64_t db, int sc) {
  asm volatile("{\n.reg .pred p;\nsetp.ne.b32 p, %130, 0;\n"
               "wgmma.mma_async.sync.aligned.m64n256k16.f32.bf16.bf16 " D128 ", %128, %129, p, 1, 1, 0, 1;\n}"
               : R128(d, e) : "l"(da), "l"(db), "r"(sc));
}
__device__ __forceinline__ void mma256_rs(float (&d)[64], float (&e)[64], uint32_t a0, uint32_t a1, uint32_t a2, uint32_t a3, uint64_t db) {
  asm volatile("{\n.reg .pred p;\nsetp.ne.b32 p, 1, 0;\n"
               "wgmma.mma_async.sync.aligned.m64n256k16.f32.bf16.bf16 " D128 ", {%128,%129,%130,%131}, %132, p, 1, 1, 1;\n}"
               : R128(d, e) : "r"(a0), "r"(a1), "r"(a2), "r"(a3), "l"(db));
}
template <int N> __device__ __forceinline__ void keep(float (&a)[N]) {
#pragma unroll
  for (int i = 0; i < N; i++) asm volatile("" : "+f"(a[i])::"memory");
}
template <int N> __device__ __forceinline__ void keep(uint32_t (&a)[N]) {
#pragma unroll
  for (int i = 0; i < N; i++) asm volatile("" : "+r"(a[i])::"memory");
}

#define STAMP(idx) do {} while (0)
#define PROF(grp, cond, idx) do {} while (0)

constexpr float SCL2 = 1.4426950408889634f * 0.08838834764831845f;

__device__ __forceinline__ void pack_p(const float (&s)[64], uint32_t (&p)[32]) {
#pragma unroll
  for (int i = 0; i < 32; i++) p[i] = pack_bf(s[2 * i], s[2 * i + 1]);
}

__device__ __forceinline__ void issue_qk(float (&s)[64], uint32_t q0, uint32_t q1, uint32_t kslot) {
  const uint64_t db = make_desc(kslot, 16, 1024), da0 = make_desc(q0, 16, 1024), da1 = make_desc(q1, 16, 1024);
#pragma unroll
  for (int kk = 0; kk < 8; kk++) mma_ss<0>(s, (kk < 4 ? da0 : da1) + (kk & 3) * 2, db + (kk >> 2) * 1024 + (kk & 3) * 2, kk != 0);
}
__device__ __forceinline__ void issue_pv(float (&o)[64], uint32_t (&p)[32], uint32_t vslot, int acc) {
  uint64_t db = make_desc(vslot, 16384, 1024);
#pragma unroll
  for (int kk = 0; kk < 8; kk++)
    mma_rs<1>(o, p[4 * kk], p[4 * kk + 1], p[4 * kk + 2], p[4 * kk + 3], db + kk * 128, kk == 0 ? acc : 1);
}

template <int H>
__device__ __forceinline__ void store_chunk(const float (&a)[64], uint32_t addr) {
#pragma unroll
  for (int i = 8 * H; i < 8 * H + 8; i += 2)
    stmatrix4(addr ^ ((i & 7) << 4), pack_bf(a[4 * i], a[4 * i + 1]), pack_bf(a[4 * i + 2], a[4 * i + 3]),
              pack_bf(a[4 * i + 4], a[4 * i + 5]), pack_bf(a[4 * i + 6], a[4 * i + 7]));
}
template <int H>
__device__ __forceinline__ void store_chunk(const float (&a)[64], float i0, float i1, uint32_t addr) {
#pragma unroll
  for (int i = 8 * H; i < 8 * H + 8; i += 2)
    stmatrix4(addr ^ ((i & 7) << 4), pack_bf(a[4 * i] * i0, a[4 * i + 1] * i0), pack_bf(a[4 * i + 2] * i1, a[4 * i + 3] * i1),
              pack_bf(a[4 * i + 4] * i0, a[4 * i + 5] * i0), pack_bf(a[4 * i + 6] * i1, a[4 * i + 7] * i1));
}
__device__ __forceinline__ float inv_quad_sum(float l) {
  l += __shfl_xor_sync(0xffffffffu, l, 1);
  l += __shfl_xor_sync(0xffffffffu, l, 2);
  return rcp(l);
}

__device__ __forceinline__ void write_table(uint32_t table, bool ca, uint32_t t, const uint4& m0, const uint4& m1) {
  float c0 = untag_sum(m0.x, m1.x), c1 = untag_sum(m0.y, m1.y), c2 = untag_sum(m0.z, m1.z), c3 = untag_sum(m0.w, m1.w);
  if (ca) { c0 = 1.f + rbf(c0); c1 = 1.f + rbf(c1); c2 = 1.f + rbf(c2); c3 = 1.f + rbf(c3); }
  const uint32_t d = table + (t >> 2) * 64 + (t & 1) * 32 + (t & 2) * 2 + (ca ? 0 : 8);
  sts1(d, pack_bf(c0, c1));
  sts1(d + 16, pack_bf(c2, c3));
}

__device__ __forceinline__ void ln_scalars(float mean, float var, float& mb, float& sd) {
  mb = rbf(mean);
  float r; asm("sqrt.approx.ftz.f32 %0, %1;" : "=f"(r) : "f"(rbf(rbf(var) + 1e-5f)));
  sd = rbf(r);
}

__global__ void __cluster_dims__(2, 1, 1) __launch_bounds__(384, 1) fused_kernel(const __grid_constant__ Maps maps, const Ptrs P) {
  extern __shared__ __align__(1024) uint8_t smem_raw[];
  const uint32_t base = smem_u32(smem_raw);
  const int tid = threadIdx.x, lane = tid & 31;
  const int warp = __shfl_sync(0xffffffffu, tid >> 5, 0);
  int b = blockIdx.x;
  if (b < NMAIN) {
    const int p = b >> 1;
    const int grp = p < 4 ? 7 : (p < 36 ? (p + 2) & 7 : (p - 30) % 7), k = p < 4 ? 4 + p : (p < 36 ? (p - 4) >> 3 : 4 + (p - 36) / 7);
    b = grp << 4 | k << 1 | (b & 1);
  }
  PROF(31, tid == 0, 0);

  if (b >= NMAIN) {
    float* sc = reinterpret_cast<float*>(smem_raw);
    float* red = sc + DM;
    for (int k = tid; k < DM; k += 384) sc[k] = rbf(silu_f(__bfloat162float(P.c[k])));
    __syncthreads();
    if (tid < 256) {
      const int col = 2048 + (b - NMAIN) * 1024 + (tid & 127) * 8, r0 = (tid >> 7) * 512;
      float acc[8];
#pragma unroll
      for (int e = 0; e < 8; e++) acc[e] = 0.f;
#pragma unroll 1
      for (int r = r0; r < r0 + 512; r += HU) {
        uint4 w[HU];
#pragma unroll
        for (int u = 0; u < HU; u++) w[u] = ldg_stream4(P.w_mod + (size_t)(r + u) * NMOD + col);
#pragma unroll
        for (int u = 0; u < HU; u++) {
          float s = sc[r + u];
          acc[0] += s * bf_lo(w[u].x); acc[1] += s * bf_hi(w[u].x); acc[2] += s * bf_lo(w[u].y); acc[3] += s * bf_hi(w[u].y);
          acc[4] += s * bf_lo(w[u].z); acc[5] += s * bf_hi(w[u].z); acc[6] += s * bf_lo(w[u].w); acc[7] += s * bf_hi(w[u].w);
        }
      }
      if (tid >= 128) {
#pragma unroll
        for (int e = 0; e < 8; e++) red[(tid & 127) * 8 + e] = acc[e];
      }
      const uint32_t tag = ld_relaxed(&g_epoch) % 3 + 1;
      bar_sync(1, 256);
      if (tid < 128) {
        uint32_t o[8];
#pragma unroll
        for (int e = 0; e < 8; e++) o[e] = __float_as_uint(rbf(acc[e] + red[tid * 8 + e])) | tag;
        st_relaxed4(g_mod + col, o[0], o[1], o[2], o[3]);
        st_relaxed4(g_mod + col + 4, o[4], o[5], o[6], o[7]);
        const uint4 wr = ldg_nc4(P.w_r + tid * 8);
        const uint32_t wv[4] = {wr.x, wr.y, wr.z, wr.w};
        float dsum = 0.f;
#pragma unroll
        for (int e = 0; e < 8; e++) {
          const float m = bf_hi(o[e]);
          dsum += (b == NMAIN + 2 ? rbf(1.f + m) : m) * ((e & 1) ? bf_hi(wv[e >> 1]) : bf_lo(wv[e >> 1]));
        }
#pragma unroll
        for (int k = 16; k > 0; k >>= 1) dsum += __shfl_xor_sync(0xffffffffu, dsum, k);
        if (lane == 0) st_relaxed(g_mod + (b - NMAIN) * 4 + warp, tagf(dsum, tag));
      }
    }
    PROF(2, tid == 0, 1);
    return;
  }

  const int rank = b & 1;
  const int rb = ((b >> 4) << 1) | rank, cj = (b >> 1) & 7;
  const bool late = b & 4;
  const uint32_t bfull = base + OFF_BAR, bempty = bfull + NSLOT * 8;
  const uint32_t gfull = bempty + NSLOT * 8, gempty = gfull + 32;
  const uint32_t bar_ofull = gempty + 32;
  const uint32_t bar_ofree = bar_ofull + 32;
  const uint32_t bar_par = bar_ofree + 32;
  const uint32_t bar_mod = bar_par + 8;
  const uint32_t bar_pread = bar_mod + 8;
  const uint32_t bar_xres = bar_pread + 8;
  const uint32_t bar_ring = bar_xres + 8;
  const uint32_t bar_box = bar_ring + 24;
  const uint32_t bar_go = bar_box + 96;
  const uint32_t bar_go2 = bar_go + 16;
  const uint32_t bar_cnt = bar_go + 24;
  const uint32_t xfull = bar_go + 40, xempty = xfull + 32;
  const uint32_t bar_hw = xempty + 32, bar_hx = bar_hw + 8;
  const uint32_t bar_hpub = bar_hx + 16;
  const uint32_t bar_win = bar_hpub + 16;
  const uint32_t bar_rx = bar_win + 8;
  const uint32_t bar_sel = bar_rx + 8;
  const uint32_t bar_gate = bar_sel + 8;
  const uint32_t bar_rel = bar_gate + 8;
  const uint32_t bar_od = bar_rel + 8;
  const uint32_t bar_mod2 = bar_od + 8;
  const uint32_t bar_res = bar_go + 8;
  const uint32_t stage = base + OFF_STAGE, par = base + OFF_PAR;

  if (warp == 10 && elect_one()) prefetch_map(&maps.wm);
  if (warp == 8 && elect_one()) {
    for (int s = 0; s < NSLOT; s++) { mbar_init(bfull + s * 8, 1); mbar_init(bempty + s * 8, 16); }
    for (int s = 0; s < 4; s++) { mbar_init(gfull + s * 8, 1); mbar_init(gempty + s * 8, 16); mbar_init(xfull + s * 8, 1); mbar_init(xempty + s * 8, 8); mbar_init(bar_ofree + s * 8, 1); mbar_init(bar_ofull + s * 8, 128); }
    mbar_init(bar_par, 64); mbar_init(bar_mod, 256); mbar_init(bar_pread, 2); mbar_init(bar_xres, 1);
    mbar_init(bar_ring, 8); mbar_init(bar_ring + 8, 8); mbar_init(bar_ring + 16, 8);
    mbar_init(bar_go, 1); mbar_init(bar_go2, 1); mbar_init(bar_cnt, 1); mbar_init(bar_cnt + 8, 1); mbar_init(bar_hpub, 8); mbar_init(bar_hpub + 8, 8); mbar_init(bar_res, 1); mbar_init(bar_win, 1); mbar_init(bar_rx, 1); mbar_init(bar_sel, 64); mbar_init(bar_gate, 8); mbar_init(bar_rel, 8); mbar_init(bar_od, 1); mbar_init(bar_mod2, 64);
    for (int s = 0; s < 12; s++) mbar_init(bar_box + s * 8, 1);
    asm volatile("fence.mbarrier_init.release.cluster;" ::: "memory");
    prefetch_map(&maps.x); prefetch_map(&maps.wq); prefetch_map(&maps.k); prefetch_map(&maps.v);
  }
  if (warp == 9 && elect_one()) {
    mbar_init(bar_hw, 1); mbar_init(bar_hx, 1); mbar_init(bar_hx + 8, 1);
    asm volatile("fence.mbarrier_init.release.cluster;" ::: "memory");
    mbar_expect_tx(bar_hw, 32768);
    mbar_expect_tx(bar_hx, 16384);
    mbar_expect_tx(bar_hx + 8, 16384);
    const __nv_bfloat16* xs = P.x + (size_t)(rb * 128 + cj * 16) * DM;
    bulk_load(base + 2 * GST_BYTES, xs, 16384, bar_hx);
    if (!late) {
      tma2d(stage, &maps.wm, (b >> 1) * 32, rank * 512, bar_hw);
      tma2d(stage + 16384, &maps.wm, (b >> 1) * 32, rank * 512 + 256, bar_hw);
    }
    bulk_load(base + 3 * GST_BYTES, xs + 8 * DM, 16384, bar_hx + 8);
  }
  cluster_arrive();

  if (warp >= 8) {
    asm volatile("setmaxnreg.dec.sync.aligned.u32 40;");
    if (warp < 10) bar_arrive(1, 320);
    const uint32_t epoch = ld_relaxed(&g_epoch);
    cluster_wait();
    if (warp == 8) {
      const int kvrow = (cj >> 1) * SK + (SK - WIN);
      int wch = cj * 8 + rank * 2;
#pragma unroll 1
      for (int ps = 0; ps < 3; ps++) {
        const CUtensorMap* mw = ps == 2 ? &maps.wo : &maps.wq;
        const uint32_t xt = ps == 1 ? XT1 : XT2, wt = ps == 0 ? WT0 : (ps == 1 ? WT1 : WT2);
        const int nst = ps == 2 ? 32 : 16;
#pragma unroll 1
        for (int i = 0; i < nst; i++) {
          const uint32_t bf = gfull + (i & 3) * 8;
          const int kt = ps == 2 ? (((cj & 1) * 4 + ((i >> 1) & 3)) * 4 + (i >> 3)) * 2 + (i & 1) : (ps ? i : slice_of(i) + (b & 14)) & 15;
          const uint32_t wd = base + unit_of(wt, i & 3) + rank * UNIT, xd = base + unit_of(xt, i & 3);
          const uint8_t* xs = g_act + (uint32_t)(rb * 80 + (ps - 1) * 16 + kt) * UNIT;
          if (ps == 0 && i == HD) mbar_wait(bar_mod, 0);
          if (ps == 2 && (i & 7) == 0 && i != 8) mbar_wait(i ? bar_cnt + i - 16 : bar_ofree + 24, 0);
          if ((i & 7) == 0) fence_async();
          if (i == RES0) mbar_wait(bar_res, 0);
          mbar_wait(bf, ((i >> 2) & 1) ^ 1);
          if (elect_one()) {
            mbar_expect_tx(bf, ps ? GST_BYTES : 2 * UNIT);
            if (ps && i < 2) bulk_load_stream(xd, xs, UNIT, bf);
            mbar_arrive_pred(bar_go, i == GOST);
            mbar_arrive_pred(bar_go2, ps == 1 && i == PG0);
            mbar_arrive_pred(bar_od, ps && i == (ps == 1 ? ODS1 : ODS) + 1);
            if (i == RES0) mbar_expect_tx(bar_xres, 32768);
          }
          const int wk = (i == 31 ? kt ^ (rank * 32) : kt) * 64, wc = i == 31 ? cj * 2 : wch;
          const uint64_t xp = i == 31 ? l2_normal() : l2_stream();
          mbar_wait(ps && i < 4 ? bempty + i * 8 : gempty + (i & 3) * 8, ((i >> 2) & 1) ^ 1);
          if (elect_one()) {
            tma3d_mc<true>(wd, mw, 0, wk, wc, bf);
            if (ps && i > 2) bulk_load_stream(xd, xs, UNIT, bf, xp);
            if (i == RES0 || i == RES1) tma2d(base + OFF_RES + (i == RES1) * UNIT, &maps.x, cj * 128 + (i == RES1) * 64, rb * 128, bar_xres);
          }
          if (ps && i == 2) {
            mbar_wait(bar_ofree + (ps - 1) * 16, 0);
            if (elect_one()) bulk_load_stream(xd, xs, UNIT, bf);
          }
        }
        if (ps == 2) break;
        wch = ps ? ((wch >> 3) ^ rank) * 2 : wch + 4;
#pragma unroll 1
        for (int u = 0; u < 16; u++) {
          const bool isk = (u == 0) || ((u & 1) && u < 15);
          const int blk = (isk ? (u + 1) >> 1 : (u == 15 ? 7 : (u >> 1) - 1)) & 3;
          const uint32_t sl = base + unit_of(ps ? AT1 : AT0, u & 3) + rank * UNIT, bf = bfull + (u & 3) * 8;
          mbar_wait(bf, ((u >> 2) & 1) ^ 1);
          if (elect_one()) mbar_expect_tx(bf, SLOT_BYTES);
          mbar_wait(u < 4 ? gempty + ((u + 1) >> 1) * 8 : bempty + (u & 3) * 8, ((u >> 2) & 1) ^ 1);
          if (elect_one()) {
            if (ps && u >= 7 && u != 8) tma3d_mc<true>(sl, isk ? &maps.k : &maps.v, 0, kvrow + blk * 128, rank, bf);
            else tma3d_mc<false>(sl, isk ? &maps.k : &maps.v, 0, kvrow + blk * 128, rank, bf);
          }
        }
      }
      if (elect_one()) mbar_expect_tx(bar_rx, UNIT);
      mbar_wait(bar_rel, 0);
      if (elect_one()) {
        bulk_load_stream(base + UNIT, g_act + (uint32_t)(rb * 80 + 16 + 63 - (cj & 1) * 32) * UNIT, UNIT, bar_rx);
      }
      if (b < NFFN) {
#pragma unroll 1
        for (int u = 0; u < 12; u++) {
          const uint32_t dst = base + unit_of(u < 4 ? FT_G : (u < 8 ? FT_U : FT_D), u & 3);
          if (elect_one()) mbar_expect_tx(bar_box + u * 8, UNIT);
          if (u == 0 || u == 2 || u == 8) mbar_wait(bar_ring + (u == 8 ? 16 : u * 4), 0);
          const int fp = u < 8 ? FPACE0 : FPACE;
          if (u >= fp) mbar_wait(bar_box + (u - fp) * 8, 0);
          if (elect_one()) {
            if (u < 8) tma2d(dst, u < 4 ? &maps.wg : &maps.wu, b * 32, (u & 3) * 256, bar_box + u * 8);
            else tma3d(dst, &maps.wd, 0, b * 32, (u - 8) * 4, bar_box + u * 8);
          }
        }
      }
    } else if (warp == 9) {
      const uint32_t target = 8 * (epoch + 1);
      uint32_t hmask = 0;
#pragma unroll 1
      for (int i = 0; i < 16; i++) {
        if (i == HDX) mbar_wait(bar_mod, 0);
        const int kt = (2 * cj + slice_of(i)) & 15;
        const uint32_t need = i == 15 ? 0xffffu : 1u << kt;
        if (i >= NRS && (hmask & need) != need) {
          uint32_t n = 0;
          do { hmask = __ballot_sync(0xffffffffu, ld_acquire(&g_cnt_h[rb * 32 + (lane & 15)]) == epoch + 1); watchdog(n); } while ((hmask & need) != need);
          PROF(1, lane == 0 && i == NRS, 26);
          fence_async();
        }
        mbar_wait(xempty + (i & 3) * 8, ((i >> 2) & 1) ^ 1);
        if (elect_one()) {
          mbar_expect_tx(xfull + (i & 3) * 8, UNIT);
          if (i < NRS) tma2d(base + (i & 3) * GST_BYTES, &maps.x, kt * 64, rb * 128, xfull + (i & 3) * 8);
          else bulk_load_stream(base + (i & 3) * GST_BYTES, g_act + (uint32_t)(rb * 80 + kt) * UNIT, UNIT, xfull + (i & 3) * 8);
        }
      }
      prefetch_map(&maps.wo);
#pragma unroll 1
      for (int t = 0; t < 4; t++) {
        if (t & 1) mbar_wait(bar_od, t >> 1);
        const int ops = OPS >> (t & 1);
#pragma unroll 1
        for (int p = 0; p < 32768; p += ops) {
          const uint32_t w = p >> 14, c = (p >> 13) & 1, off = w * 8192 + (p & 8191);
          mbar_wait(bar_ofull + (t & 1) * 16 + w * 8, t >> 1);
          if (elect_one()) {
            bulk_store(g_act + (uint32_t)(rb * 80 + 16 + (cj * 4 + t) * 2 + c) * UNIT + off, base + unit_of(QT, 2 * t + c) + off, ops);
            asm volatile("cp.async.bulk.commit_group;" ::: "memory");
            asm volatile("cp.async.bulk.wait_group.read 0;" ::: "memory");
          }
        }
        if (elect_one()) {
          mbar_arrive(t < 3 ? bar_ofree + t * 8 : bar_res);
          asm volatile("cp.async.bulk.wait_group 0;" ::: "memory");
          fence_async();
          red_release(&g_cnt_o[((rb * 4 + t) * 2 + (cj >> 2)) * 32], 2);
        }
        if (t) {
          wait_counter(&g_cnt_o[(rb * 8 + 2 * t + (cj & 1)) * 32], target);
          if (t & 1) wait_counter(&g_cnt_o[(rb * 8 + (t == 1 ? cj & 1 : 7 - (cj & 1))) * 32], target);
          if (elect_one()) mbar_arrive(t == 1 ? bar_ofree + 24 : bar_cnt + t * 8 - 16);
        }
      }
      PROF(2, lane == 0, 27);
      const uint32_t tag = epoch % 3 + 1;
      const uint32_t* inbox = g_cand + (b >> 4) % CR * 512 + (lane & 15) * CS;
      mbar_wait(bar_ring + 16, 0);
      uint32_t c0 = ld_relaxed(inbox), n = 0;
#define CAND_STEP(cv)                                                                                        \
      {                                                                                                      \
        const bool valid = (cv & 3u) == tag, all = __all_sync(0xffffffffu, valid);                           \
        const uint32_t best = __reduce_max_sync(0xffffffffu, valid ? cv : 0u);                               \
        const uint32_t blk = __ffs(__ballot_sync(0xffffffffu, cv == best)) - 1;                              \
        if (best) sts2(par + PAR_CONST + 56, best, (blk << 7 | (~best >> 2 & 127)) | (all ? 0x1800 : 0x800)); \
        if (all) break;                                                                                      \
        cv = ld_relaxed(inbox);                                                                              \
      }
      while (true) { CAND_STEP(c0) watchdog(n); }
    } else {
      const int t2 = tid - 320;
      if (late && warp == 10) {
        mbar_wait(bar_hx, 0);
        if (elect_one()) {
          tma2d(stage, &maps.wm, (b >> 1) * 32, rank * 512, bar_hw);
          tma2d(stage + 16384, &maps.wm, (b >> 1) * 32, rank * 512 + 256, bar_hw);
        }
      }
      {
        const uint32_t tag = epoch % 3 + 1;
        mbar_wait(bar_hx + 8, 0);
        mbar_wait(bar_hw, 0);
        __nanosleep(late ? OSL2 : OSL);
        {
          const uint32_t t7 = (warp & 1) * 64 + (lane >> 4) * 32 + 16 + (lane & 15);
          const uint32_t* pm = g_modp + ((cj * 128 + t7 * 4) & (DM - 1));
          uint4 m0, m1, m2, m3;
          uint32_t n = 0;
          do {
            m0 = ld_relaxed4(pm); m1 = ld_relaxed4(pm + 2 * DM); m2 = ld_relaxed4(pm + DM); m3 = ld_relaxed4(pm + 3 * DM);
            watchdog(n);
          } while (!__all_sync(0xffffffffu, tag_ok(m0, tag) && tag_ok(m1, tag) && tag_ok(m2, tag) && tag_ok(m3, tag)));
          write_table(par, false, t7, m0, m1);
          write_table(par, true, t7, m2, m3);
          mbar_arrive(bar_mod2);
        }
      }
      mbar_wait(bar_hpub + (warp & 1) * 8, 0);
      PROF(1, t2 == 0, 24);
#pragma unroll 1
      for (int c = 0; c < 8; c++) {
        const uint32_t off = (warp & 1) * UNIT + c * 2048 + lane * 16;
        uint8_t* dst = g_act + (uint32_t)(rb * 80 + cj * 2) * UNIT + off;
        const uint4 v0 = lds4(stage + off), v1 = lds4(stage + off + 512), v2 = lds4(stage + off + 1024), v3 = lds4(stage + off + 1536);
        stg4(dst, v0); stg4(dst + 512, v1); stg4(dst + 1024, v2); stg4(dst + 1536, v3);
      }
      __syncwarp();
      PROF(1, t2 == 0, 15);
      if (lane == 0) {
        mbar_arrive(bar_pread);
        red_release(&g_cnt_h[rb * 32 + cj * 2 + (warp & 1)], 1);
        PROF(1, t2 == 0, 25);
        prefetch_map(&maps.wg); prefetch_map(&maps.wu); prefetch_map(&maps.wd); prefetch_map(&maps.out);
      }
      __syncwarp();
      if (b < NFFN) {
        mbar_wait(bar_go2, 0);
        const __nv_bfloat16* pg = ((b & 1) ? P.w_up : P.w_gate) + (b >> 1) * 64 + (size_t)t2 * FF;
        const __nv_bfloat16* pd = P.w_down + (size_t)b * 32768 + t2 * 64;
        PROF(2, t2 == 0, 13);
#pragma unroll 1
        for (int i = 0; i < WN; i += WB) {
          uint32_t v[WB];
#pragma unroll
          for (int u = 0; u < WB; u++) {
            const int k = i + u;
            asm volatile("ld.global.cg.L2::128B.u32 %0, [%1];" : "=r"(v[u]) : "l"(k < 16 ? pg + (size_t)k * 64 * FF : pd + (k - 16) * 4096));
          }
#pragma unroll
          for (int u = 1; u < WB; u++) v[0] ^= v[u];
          sts1(par + PAR_SINK + t2 * 4, v[0]);
        }
        PROF(2, t2 == 0, 14);
      }
      const uint32_t tag = epoch % 3 + 1;
      mbar_wait(bar_go, 0);
      bar_sync(4, 64);
      if (warp == 10) {
        const uint32_t* src = g_mod + 2 * DM + cj * 128 + lane * 4;
        const uint2 wr = *reinterpret_cast<const uint2*>(P.w_r + cj * 128 + lane * 4);
        uint4 vga, vsb, vcb, vgb;
        uint32_t n = 0;
        do {
          vga = ld_relaxed4(src); vsb = ld_relaxed4(src + DM); vcb = ld_relaxed4(src + 2 * DM); vgb = ld_relaxed4(src + 3 * DM);
          watchdog(n);
        } while (!__all_sync(0xffffffffu, tag_ok(vga, tag) && tag_ok(vsb, tag) && tag_ok(vcb, tag) && tag_ok(vgb, tag)));
        const float c0 = rbf(1.f + bf_hi(vcb.x)), c1 = rbf(1.f + bf_hi(vcb.y)), c2 = rbf(1.f + bf_hi(vcb.z)), c3 = rbf(1.f + bf_hi(vcb.w));
        const float a0 = c0 * bf_lo(wr.x), a1 = c1 * bf_hi(wr.x), a2 = c2 * bf_lo(wr.y), a3 = c3 * bf_hi(wr.y);
        const uint32_t h0 = pack_bf(a0, a1), h1 = pack_bf(a2, a3);
        const uint32_t t1 = par + PAR_T1 + (lane >> 2) * 64 + (lane & 1) * 32 + (lane & 2) * 2;
        sts1(t1, h0); sts1(t1 + 8, pack_bf(a0 - bf_lo(h0), a1 - bf_hi(h0)));
        sts1(t1 + 16, h1); sts1(t1 + 24, pack_bf(a2 - bf_lo(h1), a3 - bf_hi(h1)));
        const uint32_t tg = par + PAR_SINK + (lane >> 3) * 64 + (lane & 1) * 32 + (lane & 6) * 2;
        sts1(tg, __byte_perm(vga.x, vga.y, 0x7632)); sts1(tg + 16, __byte_perm(vga.z, vga.w, 0x7632));
        sts4(par + PAR_T2 + lane * 32, make_uint4(pack_bf(c0, c1), __byte_perm(vsb.x, vsb.y, 0x7632), __byte_perm(vgb.x, vgb.y, 0x7632), __byte_perm(vga.x, vga.y, 0x7632)));
        sts4(par + PAR_T2 + lane * 32 + 16, make_uint4(pack_bf(c2, c3), __byte_perm(vsb.z, vsb.w, 0x7632), __byte_perm(vgb.z, vgb.w, 0x7632), __byte_perm(vga.z, vga.w, 0x7632)));
      } else {
        const uint4 g = poll4((lane & 8) ? g_mod + 8 - (lane & 1) * 4 : g_mod + 5 * DM + (b >> 4) * 128 + (lane & 7) * 16 + (b & 12), tag);
        sts1(par + PAR_CONST + 60, 0);
        if (lane < 8) sts1(par + PAR_CONST + 16 + lane * 4, (b & 2) ? ((b & 1) ? g.w : g.z) : ((b & 1) ? g.y : g.x));
        else if (lane < 10) sts2(par + PAR_CONST + (lane - 8) * 8, __float_as_uint(untag_sum(g.x, g.y) + untag_sum(g.z, g.w)), epoch);
      }
      __syncwarp();
#pragma unroll 1
      for (int q = 0; q < 32; q++) {
        st_b128(g_xch + ((size_t)b * 8 * 256 + q * 64 + t2) * 4, (epoch & 1) << 16, 0, 0, 0);
        __nanosleep(RSL);
      }
      for (int q = 0; q < 2; q++) st_relaxed4(g_stats + (((rb * 8 + q * 4 + (t2 >> 4)) * 8 + cj) * 16 + (t2 & 15)) * 4, 0, 0, 0, 0);
      if (b < NFFN)
        for (int q = 0; q < 2; q++) st_relaxed4(ypart_slot(b, q * 64 + t2), 0, 0, 0, 0);
      st_relaxed4(g_row + rb * 2 * DM + (t2 >> 5) * DM + cj * 128 + (t2 & 31) * 4, 0, 0, 0, 0);
      __threadfence();
      mbar_arrive(bar_par);
      mbar_wait(bar_gate, 0);
      uint32_t have = 0, n = 0;
      while (true) {
        const uint32_t st = lds1(par + PAR_CONST + 60) >> 7;
        if ((st & 31) != have) {
          const uint32_t* hsrc = g_row + (st & 15) * 2 * DM + t2 * 4;
          uint4 hv[4];
          bool ok = true;
#pragma unroll
          for (int i = 0; i < 4; i++) hv[i] = ld_pairs(hsrc + i * 256);
#pragma unroll
          for (int i = 0; i < 4; i++) {
            sts2(base + ((FT_G >> i * 4) & 15) * UNIT + (warp & 1) * 8192 + 256 + lane * 8, hv[i].x, hv[i].z);
            ok = ok && hv[i].y == tag && hv[i].w == tag;
          }
          have = __all_sync(0xffffffffu, ok) ? st & 31 : 0;
        }
        if ((st ^ have) == 32) break;
        watchdog(n);
      }
      mbar_arrive(bar_sel);
    }
    __syncwarp();
    cluster_arrive();
    {
      const uint32_t tag = epoch % 3 + 1, t3 = tid - 256;
      mbar_wait(bar_win, 0);
      uint2 win = lds2(par + PAR_CONST + 56);
      win.y &= 0x7ff;
      const uint32_t* fsrc = g_row + (win.y >> 7) * 2 * DM + (b >> 4) * 128 + (t3 & 7) * 16 + (b & 6) * 2 + ((b >> 2) & 2);
      const uint32_t* ysrc = ypart_slot(min(t3, NFFN - 1), b);
      uint2 fh = ld_pair(fsrc), fx = ld_pair(fsrc + DM);
      uint4 ya = ld_b128(ysrc);
      const float rwin = __uint_as_float(((int)win.x < 0 ? win.x & 0x7fffffffu : ~win.x) & ~0x1ffu);
      const float rs = rbf(rcp(1.f + __expf(-rbf(rwin))));
      uint32_t n = 0;
      while (__any_sync(0xffffffffu, fh.y != tag || fx.y != tag)) { fh = ld_pair(fsrc); fx = ld_pair(fsrc + DM); watchdog(n); }
      while (true) {
        const bool miss = ((ya.x & 1) | (ya.y & 1) << 1) != tag;
        if (!__any_sync(0xffffffffu, miss)) break;
        if (miss) ya = ld_b128(ysrc);
        watchdog(n);
      }
      PROF(8, t3 == 0, 5);
      float y[8] = {bf_lo(ya.x & ~1u), bf_hi(ya.x), bf_lo(ya.y & ~1u), bf_hi(ya.y), bf_lo(ya.z), bf_hi(ya.z), bf_lo(ya.w), bf_hi(ya.w)};
#pragma unroll
      for (int h = 4; h > 0; h >>= 1) {
        const bool up = lane & (h * 2);
#pragma unroll
        for (int e = 0; e < h; e++) y[e] = (up ? y[e + h] : y[e]) + __shfl_xor_sync(0xffffffffu, up ? y[e] : y[e + h], h * 2);
      }
      y[0] += __shfl_xor_sync(0xffffffffu, y[0], 1);
      if (!(lane & 1)) sts1(par + PAR_RED + 64 + t3 * 2, __float_as_uint(y[0]));
      bar_sync(4, 128);
      if (t3 < 8) {
        float y0 = 0.f;
#pragma unroll
        for (int w7 = 0; w7 < 7; w7++) y0 += __uint_as_float(lds1(par + PAR_RED + 64 + w7 * 32 + t3 * 4));
        const uint32_t gv = lds1(par + PAR_CONST + 16 + t3 * 4);
        const uint32_t upd = hmul2(pack_bf(y0, y0), pack_bf(rs, rs));
        const uint32_t r = hadd2(fx.x, hmul2(__byte_perm(gv, gv, 0x3232), hadd2(fh.x, upd)));
        reinterpret_cast<uint16_t*>(P.out)[(size_t)win.y * DM + (b >> 4) * 128 + t3 * 16 + (b & 15)] = (b & 1) ? r >> 16 : r;
        if (b == 0 && t3 == 0) st_relaxed(&g_epoch, epoch + 1);
      }
      PROF(31, t3 == 0, 36);
    }
    cluster_wait();
  } else {
    const int wg = warp >> 2;

    uint32_t tag;
    {
      uint32_t* const pmod = g_modp + rank * 2 * DM + (b >> 1) * 32 + lane;
      uint32_t* const pln = g_ln1 + (rb * 128 + cj * 16 + warp) * 4;
      uint32_t sc[8];
#pragma unroll
      for (int k = 0; k < 8; k++) sc[k] = ldg_nc1(P.c + rank * 512 + warp * 64 + k * 8 + (lane & 3) * 2);
      const uint32_t epoch = ld_relaxed(&g_epoch);
      if (warp == 0) st_relaxed(pmod, 0);
      if (lane == 0) { st_b128(pln, 0, 0, 0, 0); st_b128(pln + 32, 0, 0, 0, 0); }
      asm volatile("setmaxnreg.inc.sync.aligned.u32 232;");
      bar_sync(1, 320);
#pragma unroll
      for (int k = 0; k < 8; k++) sc[k] = pack_bf(silu_f(bf_lo(sc[k])), silu_f(bf_hi(sc[k])));
      keep(sc);
      tag = epoch % 3 + 1;
#pragma unroll
      for (int part = 0; part < 4; part++) {
        if (!(part & 1)) {
          const uint32_t xa = base + (2 + part / 2) * GST_BYTES + warp * 2048 + lane * 16;
          mbar_wait(bar_hx + part * 4, 0);
          float s0 = 0.f, s1 = 0.f, q0 = 0.f, q1 = 0.f;
#pragma unroll
          for (int q = 0; q < 4; q++) {
            const uint4 xv = lds4(xa + q * 512);
            const uint32_t u[4] = {xv.x, xv.y, xv.z, xv.w};
#pragma unroll
            for (int e = 0; e < 4; e++) { const float lo = bf_lo(u[e]), hi = bf_hi(u[e]); s0 += lo; s1 += hi; q0 += lo * lo; q1 += hi * hi; }
          }
          s0 += s1; q0 += q1;
#pragma unroll
          for (int o = 16; o > 0; o >>= 1) { s0 += __shfl_xor_sync(0xffffffffu, s0, o); q0 += __shfl_xor_sync(0xffffffffu, q0, o); }
          const float mean = s0 * (1.f / DM);
          float mb, sd;
          ln_scalars(mean, fmaxf(q0 * (1.f / DM) - mean * mean, 0.f), mb, sd);
          uint32_t ih, il;
          split_inv(sd, ih, il);
          if (lane == 0) st_b128(pln + part * 16, pack_bf(mb, mb), ih, il, tag);
          PROF(1, tid == 0 && part == 2, 4);
        } else if (late == (part == 3)) {
          const uint32_t fr = (lane & 7) + (lane >> 4) * 8, tq = lane & 3;
          const uint32_t wa = stage + warp * 4096 + fr * 64 + ((((lane >> 3) & 1) ^ ((fr >> 1) & 3)) << 4);
          float d0[4] = {0.f, 0.f, 0.f, 0.f}, d1[4] = {0.f, 0.f, 0.f, 0.f};
          mbar_wait(bar_hw, 0);
#pragma unroll
          for (int ks = 0; ks < 4; ks++) {
            uint32_t w[8];
            ldmatrix4t(wa + ks * 1024, w[0], w[1], w[2], w[3]);
            ldmatrix4t((wa ^ 32) + ks * 1024, w[4], w[5], w[6], w[7]);
            mma16816(d0, w[0], w[1], w[2], w[3], sc[2 * ks], sc[2 * ks + 1]);
            mma16816(d1, w[4], w[5], w[6], w[7], sc[2 * ks], sc[2 * ks + 1]);
          }
          sts1(base + 2 * GST_BYTES + warp * 2048 + (tq * 8 + (lane >> 2)) * 4, __float_as_uint((tq & 2) ? ((tq & 1) ? d1[2] : d1[0]) : ((tq & 1) ? d0[2] : d0[0])));
          bar_sync(1, 256);
          if (warp == 0) {
            float s = 0.f;
#pragma unroll
            for (int w8 = 0; w8 < 8; w8++) s += __uint_as_float(lds1(base + 2 * GST_BYTES + w8 * 2048 + lane * 4));
            st_relaxed(pmod, (__float_as_uint(s) & ~3u) | tag);
          }
          PROF(1, tid == 0, 3);
        }
      }
      cluster_wait();
      if (wg == 1) bar_arrive(2, 256);
    }

    float f0 = 0.f, f1 = 0.f;
    const uint32_t rempty = lane < 2 ? mapa(bempty, lane & 1) : 0;
    constexpr uint32_t GE = NSLOT * 8 + 32;
    float o[64], s[64];
#pragma unroll 1
    for (int ps = 0; ps < 3; ps++) {
      {
        const uint32_t xt = ps == 1 ? XT1 : XT2, wt = ps == 1 ? WT1 : WT2;
        const int nst = ps == 2 ? 28 : 14;
        if (ps == 0) {
          float ga[64], gb[64];
#pragma unroll
          for (int i = 0; i < 64; i++) { ga[i] = 0.f; gb[i] = 0.f; }
          uint32_t a[2][16];
          const uint32_t l = fresh_lane();
          uint32_t fa[4];
#pragma unroll
          for (int kk = 0; kk < 4; kk++) fa[kk] = (base + wg * 8192 + frag_offset(warp)) ^ (kk * 32);
          const uint32_t mt = par + (l & 3) * 16;
          auto fetch = [&](int i, uint32_t (&f)[16], uint32_t z) {
            mbar_wait(xfull + (i & 3) * 8, i >> 2);
#pragma unroll
            for (int kk = 0; kk < 4; kk++) ldmatrix4(fa[kk] + (i & 3) * GST_BYTES + z, f[4 * kk], f[4 * kk + 1], f[4 * kk + 2], f[4 * kk + 3]);
          };
          const bool oddw = warp & 2;
          uint4 r0, r1;
          {
            const uint32_t t7 = (warp & 1) * 64 + (l >> 4) * 32 + (l & 15);
            const uint32_t* pm = g_modp + wg * DM + ((cj * 128 + t7 * 4) & (DM - 1));
            const uint32_t* pr = g_ln1 + (rb * 128 + warp * 16 + (l >> 2)) * 4;
            uint4 m0 = make_uint4(tag, tag, tag, tag), m1 = m0;
            if (!oddw) { m0 = ld_relaxed4(pm); m1 = ld_relaxed4(pm + 2 * DM); }
            r0 = ld_b128(pr); r1 = ld_b128(pr + 32);
            fetch(0, a[0], 0); fetch(1, a[1], 0);
            uint32_t n = 0;
            bool written = false;
#pragma unroll 1
            while (true) {
              uint32_t miss;
              asm volatile("{ .reg .pred p0, p1, p2, p3; .reg .b32 t, u;\n"
                           "lop3.b32 t, %1, %2, %19, 0x7e; lop3.b32 u, %3, %4, %19, 0x7e; or.b32 t, t, u; and.b32 t, t, 3; setp.ne.u32 p0, t, 0;\n"
                           "lop3.b32 t, %5, %6, %19, 0x7e; lop3.b32 u, %7, %8, %19, 0x7e; or.b32 t, t, u; and.b32 t, t, 3; setp.ne.u32 p1, t, 0;\n"
                           "setp.ne.u32 p2, %12, %19; setp.ne.u32 p3, %16, %19;\n"
                           "@p0 ld.relaxed.gpu.global.v4.u32 {%1, %2, %3, %4}, [%17];\n"
                           "@p1 ld.relaxed.gpu.global.v4.u32 {%5, %6, %7, %8}, [%17 + 8192];\n"
                           "@p2 ld.relaxed.gpu.global.v4.u32 {%9, %10, %11, %12}, [%18];\n"
                           "@p3 ld.relaxed.gpu.global.v4.u32 {%13, %14, %15, %16}, [%18 + 128];\n"
                           "or.pred p0, p0, p1; or.pred p2, p2, p3; vote.sync.any.pred p0, p0, 0xffffffff; vote.sync.any.pred p2, p2, 0xffffffff;\n"
                           "selp.u32 t, 1, 0, p0; selp.u32 u, 2, 0, p2; or.b32 %0, t, u; }"
                           : "=r"(miss), "+r"(m0.x), "+r"(m0.y), "+r"(m0.z), "+r"(m0.w), "+r"(m1.x), "+r"(m1.y), "+r"(m1.z), "+r"(m1.w),
                             "+r"(r0.x), "+r"(r0.y), "+r"(r0.z), "+r"(r0.w), "+r"(r1.x), "+r"(r1.y), "+r"(r1.z), "+r"(r1.w)
                           : "l"(pm), "l"(pr), "r"(tag) : "memory");
              if (!(miss & 1) && !written) {
                written = true;
                if (!oddw) write_table(par, wg, t7, m0, m1);
                mbar_arrive(bar_mod);
              }
              if (!miss) break;
              watchdog(n);
            }
          }
          const uint32_t zero = r0.w ^ tag;
          auto normalize = [&](uint32_t (&f)[16]) {
#pragma unroll
            for (int k = 0; k < 16; k += 2) { f[k] = ln_norm(f[k], r0.x, r0.y, r0.z); f[k + 1] = ln_norm(f[k + 1], r1.x, r1.y, r1.z); }
          };
          auto modulate = [&](int i, uint32_t (&f)[16]) {
#pragma unroll
            for (int kk = 0; kk < 4; kk++) {
              const uint4 m = lds4(mt + slice_of(i) * 256 + kk * 64);
              f[4 * kk] = hfma2(f[4 * kk], m.x, m.z); f[4 * kk + 1] = hfma2(f[4 * kk + 1], m.x, m.z);
              f[4 * kk + 2] = hfma2(f[4 * kk + 2], m.y, m.w); f[4 * kk + 3] = hfma2(f[4 * kk + 3], m.y, m.w);
            }
            keep(f);
            mbar_arrive_pred(xempty + (i & 3) * 8, l == 0);
          };
          auto publish = [&](int u, uint32_t (&f)[16]) {
#pragma unroll
            for (int kk = 0; kk < 4; kk++) stmatrix4(fa[kk] + OFF_STAGE + u * UNIT, f[4 * kk], f[4 * kk + 1], f[4 * kk + 2], f[4 * kk + 3]);
            __syncwarp();
            mbar_arrive_pred(bar_hpub + u * 8, l == 0);
          };
          auto multiply = [&](int i, uint32_t (&f)[16]) {
            mbar_wait(gfull + (i & 3) * 8, i >> 2);
            const uint64_t db = make_desc(base + (i & 3) * GST_BYTES + UNIT, 8192, 1024);
            wg_fence();
#pragma unroll
            for (int kk = 0; kk < 4; kk++) mma256_rs(ga, gb, f[4 * kk], f[4 * kk + 1], f[4 * kk + 2], f[4 * kk + 3], db + kk * 128);
            wg_commit();
          };
          auto next = [&](int i, uint32_t (&f)[16]) {
            wg_wait<1>();
            mbar_arrive_cl(rempty, GE + ((i + 2) & 3) * 8);
            uint32_t z = zero;
#pragma unroll
            for (int k = 0; k < 16; k += 2) asm volatile("lop3.b32 %0, %1, %2, %0, 0xA8;" : "+r"(z) : "r"(f[k]), "r"(f[k + 1]));
            fetch(i, f, z);
            normalize(f);
            if (i == 2) { keep(f); mbar_wait(bar_mod2, 0); }
            modulate(i, f); multiply(i, f);
          };
          normalize(a[0]); normalize(a[1]);
          keep(a[0]); keep(a[1]);
          mbar_wait(bar_mod, 0);
          PROF(1, tid == 0, 2);
          modulate(0, a[0]); multiply(0, a[0]); publish(0, a[0]);
          modulate(1, a[1]); multiply(1, a[1]);
#pragma unroll 1
          for (int i = 2; i < NRS; i += 2) {
            next(i, a[0]);
            if (i == 2) publish(1, a[0]);
            next(i + 1, a[1]);
          }
          wg_wait<1>();
          mbar_arrive_cl(rempty, GE + ((NRS + 2) & 3) * 8);
#pragma unroll 1
          for (int i = NRS; i < 14; i++) {
            mbar_wait(xfull + (i & 3) * 8, (i >> 2) & 1);
            mbar_wait(gfull + (i & 3) * 8, (i >> 2) & 1);
            const uint32_t xa = base + (i & 3) * GST_BYTES;
            const uint64_t da = make_desc(xa + wg * 8192, 16, 1024), db = make_desc(xa + UNIT, 8192, 1024);
            if (i == 13) bar_sync(2 + wg, 256);
            wg_fence();
#pragma unroll
            for (int kk = 0; kk < 4; kk++) mma256_ss(ga, gb, da + kk * 2, db + kk * 128, 1);
            wg_commit();
            if (i == 13) bar_arrive(3 - wg, 256);
            wg_wait<1>();
            uint32_t z = zero;
#pragma unroll
            for (int k = 0; k < 16; k += 2) asm volatile("lop3.b32 %0, %1, %2, %0, 0xA8;" : "+r"(z) : "r"(a[1][k]), "r"(a[1][k + 1]));
            mbar_arrive_cl(rempty, GE + ((i + 3) & 3) * 8 + z);
            mbar_arrive_pred(xempty + ((i + 3) & 3) * 8, l == 0 && i != NRS);
          }
          mbar_wait(xfull + 16, 1);
          wg_wait<0>();
          keep(ga); keep(gb);
#pragma unroll
          for (int i = 0; i < 64; i++) {
            asm volatile("mov.b32 %0, %1;" : "=f"(s[i]) : "f"(ga[i]));
            asm volatile("mov.b32 %0, %1;" : "=f"(o[i]) : "f"(gb[i]));
          }
        } else {
          float ga[64], gb[64];
#pragma unroll
          for (int i = 0; i < 64; i++) {
            asm volatile("mov.b32 %0, %1;" : "=f"(ga[i]) : "f"(s[i]));
            asm volatile("mov.b32 %0, %1;" : "=f"(gb[i]) : "f"(o[i]));
          }
#pragma unroll 1
          for (int i = 0; i < nst; i++) {
            mbar_wait(gfull + (i & 3) * 8, (i >> 2) & 1);
            const uint64_t da = make_desc(base + unit_of(xt, i & 3) + wg * 8192, 16, 1024), db = make_desc(base + unit_of(wt, i & 3), 8192, 1024);
            if (i == nst - 1) bar_sync(2 + wg, 256);
            wg_fence();
#pragma unroll
            for (int kk = 0; kk < 4; kk++) mma256_ss(ga, gb, da + kk * 2, db + kk * 128, kk ? 1 : i);
            wg_commit();
            if (i == nst - 1) bar_arrive(3 - wg, 256);
            wg_wait<1>();
            mbar_arrive_cl(rempty, GE + ((i + 3) & 3) * 8, i != 0);
            PROF(4, tid == 0 && (i & 3) == 0, 40 + (ps - 1) * 4 + i / 4);
          }
          wg_wait<0>();
          keep(ga); keep(gb);
#pragma unroll
          for (int i = 0; i < 64; i++) {
            asm volatile("mov.b32 %0, %1;" : "=f"(s[i]) : "f"(ga[i]));
            asm volatile("mov.b32 %0, %1;" : "=f"(o[i]) : "f"(gb[i]));
          }
        }
        mbar_arrive_cl(rempty, GE + (ps == 2 ? 24 : 8));
        if (ps == 2) break;
      }
      const uint32_t qw = base + wg * 8192, qt = QT >> (16 * ps), at = ps ? AT1 : AT0;
      {
        const uint32_t wt = ps ? WT1 : WT0;
        const uint64_t da0 = make_desc(qw + unit_of(qt, 2), 16, 1024), da1 = make_desc(qw + unit_of(qt, 3), 16, 1024);
        const uint64_t db0 = make_desc(base + unit_of(wt, 2), 8192, 1024), db1 = make_desc(base + unit_of(wt, 3), 8192, 1024);
        mbar_wait(gfull + 16, 1);
        bar_sync(2 + wg, 256);
        wg_fence();
#pragma unroll
        for (int kk = 0; kk < 4; kk++) mma_ss<1>(s, da0 + kk * 2, db0 + kk * 128, 1);
        wg_commit();
        mbar_wait(xfull + 24, 1);
        mbar_wait(gfull + 24, 1);
        wg_fence();
#pragma unroll
        for (int kk = 0; kk < 4; kk++) mma_ss<1>(s, da1 + kk * 2, db1 + kk * 128, 1);
        wg_commit();
        bar_arrive(3 - wg, 256);
        mbar_wait(ps == 0 ? bar_pread : bar_ofree + 8, 0);
        wg_wait<0>();
        keep(s);
        PROF(2, tid == 0, 8 + ps * 8);
        uint32_t q[32];
        pack_p(s, q);
#pragma unroll
        for (int i = 0; i < 4; i++) stmatrix4((qw + unit_of(qt, 0) + frag_offset(warp)) ^ (i << 5), q[4 * i], q[4 * i + 1], q[4 * i + 2], q[4 * i + 3]);
        keep(q);
        bar_sync(2 + wg, 256);
        wg_fence();
#pragma unroll
        for (int kk = 0; kk < 8; kk++) mma_ss<1>(o, (kk < 4 ? da0 : da1) + (kk & 3) * 2, (kk < 4 ? db0 : db1) + UNIT / 16 + (kk & 3) * 128, 1);
        wg_commit();
        mbar_wait(bfull, 0);
        wg_fence();
        const uint64_t dk = make_desc(base + unit_of(at, 0), 16, 1024);
#pragma unroll
        for (int kk = 0; kk < 8; kk++) mma_rs<0>(s, q[4 * kk], q[4 * kk + 1], q[4 * kk + 2], q[4 * kk + 3], dk + (kk >> 2) * 1024 + (kk & 3) * 2, kk != 0);
        wg_commit();
        bar_arrive(3 - wg, 256);
#pragma unroll
        for (int i = 4; i < 8; i++) stmatrix4((qw + unit_of(qt, 1) + frag_offset(warp)) ^ ((i & 3) << 5), q[4 * i], q[4 * i + 1], q[4 * i + 2], q[4 * i + 3]);
        wg_wait<1>();
        keep(o);
        mbar_arrive_cl(rempty, GE + 16);
        mbar_arrive_cl(rempty, GE + 24);
        store_chunk<0>(o, qw + unit_of(qt, 2) + frag_offset(warp));
        store_chunk<1>(o, qw + unit_of(qt, 3) + frag_offset(warp));
        wg_wait<0>();
        keep(s);
        mbar_arrive_cl(rempty, 0);
      }
      PROF(4, tid == 0 && ps == 1, 61);
      float l0 = 0.f, l1 = 0.f;
      auto step = [&](auto odd_c, const int j, uint32_t (&pw)[32], uint32_t (&pr)[32]) {
        constexpr bool ODD = decltype(odd_c)::value;
        const bool first = !ODD && (j & 2) == 0, last = ODD && j == 7;
        const uint32_t ph = (j >> 1) & 1;
        float i0, i1, a0, a1;
        const bool so = !ODD && j == 4;
        if (so) { i0 = inv_quad_sum(l0); i1 = inv_quad_sum(l1); l0 = 0.f; l1 = 0.f; }
        bool redo = !ODD && (j | ps) == 0;
        while (true) {
          if (redo) {
            float m0 = fmaxf(s[0], s[1]), m1 = fmaxf(s[2], s[3]);
#pragma unroll
            for (int i = 1; i < 16; i++) { m0 = fmaxf(m0, fmaxf(s[4 * i], s[4 * i + 1])); m1 = fmaxf(m1, fmaxf(s[4 * i + 2], s[4 * i + 3])); }
            m0 = fmaxf(m0, __shfl_xor_sync(0xffffffffu, m0, 1)); m1 = fmaxf(m1, __shfl_xor_sync(0xffffffffu, m1, 1));
            m0 = fmaxf(m0, __shfl_xor_sync(0xffffffffu, m0, 2)); m1 = fmaxf(m1, __shfl_xor_sync(0xffffffffu, m1, 2));
            m0 *= SCL2; m1 *= SCL2;
            if (!first) {
              m0 = fmaxf(m0, f0); m1 = fmaxf(m1, f1);
              const float c0 = ex2(f0 - m0), c1 = ex2(f1 - m1);
              l0 *= c0; l1 *= c1;
              wg_wait<0>();
              keep(o);
#pragma unroll
              for (int i = 0; i < 16; i++) { o[4 * i] *= c0; o[4 * i + 1] *= c0; o[4 * i + 2] *= c1; o[4 * i + 3] *= c1; }
            }
            f0 = m0; f1 = m1;
          }
          float b0 = 0.f, b1 = 0.f;
          a0 = 0.f; a1 = 0.f;
#pragma unroll
          for (int i = 0; i < 16; i++) {
            const float e0 = ex2(fmaf(s[4 * i], SCL2, -f0)), e1 = ex2(fmaf(s[4 * i + 1], SCL2, -f0));
            const float e2 = ex2(fmaf(s[4 * i + 2], SCL2, -f1)), e3 = ex2(fmaf(s[4 * i + 3], SCL2, -f1));
            a0 += e0; b0 += e1; a1 += e2; b1 += e3;
            pw[2 * i] = pack_bf(e0, e1); pw[2 * i + 1] = pack_bf(e2, e3);
            if (i == VREL) {
#pragma unroll
              for (int k = 0; k < 2 * VREL + 2; k++) asm volatile("" : "+r"(pw[k])::"memory");
              mbar_wait(bar_mod, 0);
              wg_wait<0>();
              mbar_arrive_cl(rempty, ODD ? 16 : 0, !redo && (ODD || j));
#pragma unroll
              for (int k = 4 * VREL + 4; k < 64; k++) asm volatile("" : "+f"(s[k])::"memory");
            }
          }
          a0 += b0; a1 += b1;
          if (redo) break;
          redo = __any_sync(0xffffffffu, !(a0 + a1 < 0x1p90f) || (!ODD && fminf(a0, a1) < (first ? 0x1p-90f : 0.f)));
          if (!redo) break;
        }
        l0 += a0; l1 += a1;
        keep(pw);
        keep(o);
        if (so) store_chunk<0>(o, i0, i1, qw + unit_of(qt, 0) + frag_offset(warp));
        keep(o);
        if (j == (ODD ? 5 : 0)) { fence_async_smem(); if (ODD) mbar_arrive(bar_ofull + wg * 8); }
        mbar_wait(bfull + (ODD ? 24 : 8), ph);
        bar_sync(2 + wg, 256);
        if (!last) {
          const uint32_t qn = qt >> (j >= 3 ? 8 : 0);
          wg_fence();
          issue_qk(s, qw + unit_of(qn, 0), qw + unit_of(qn, 1), base + unit_of(at, ODD ? 3 : 1));
          wg_commit();
          mbar_wait(bfull + (ODD ? 0 : 16), ODD ? ph ^ 1 : ph);
        }
        if (so) { store_chunk<1>(o, i0, i1, qw + unit_of(qt, 1) + frag_offset(warp)); keep(o); }
        wg_fence();
        issue_pv(o, pw, base + unit_of(at, ODD ? (last ? 3 : 0) : 2), !first);
        wg_commit();
        bar_arrive(3 - wg, 256);
        wg_wait<1>();
        keep(s);
        mbar_arrive_cl(rempty, ODD ? 24 : 8, !last);
        PROF(4, tid == 0 && ps == 1, 51 + j);
      };
      uint32_t pa[32], pb[32];
#pragma unroll 1
      for (int j = 0; j < 8; j += 2) {
        step(std::false_type{}, j, pa, pb);
        step(std::true_type{}, j + 1, pb, pa);
      }
      {
        const float i0 = inv_quad_sum(l0), i1 = inv_quad_sum(l1);
        wg_wait<0>();
        keep(o);
        mbar_arrive_cl(rempty, 24);
        store_chunk<0>(o, i0, i1, qw + unit_of(qt, 2) + frag_offset(warp));
        store_chunk<1>(o, i0, i1, qw + unit_of(qt, 3) + frag_offset(warp));
        fence_async_smem();
        mbar_arrive(bar_ofull + 16 + wg * 8);
      }
      PROF(2, tid == 0, 10 + ps * 8);
    }

    const int ln = fresh_lane(), g = ln >> 2, tq = ln & 3, ct = warp * 32 + ln;
    const bool lane0 = ln == 0;
    const int lrow0 = warp * 16 + g;
    const uint32_t res = base + OFF_RES, trow = res + wg * 8192 + frag_offset(warp);
    uint32_t xr[32];
    uint4 sv[4], own;
    uint32_t* const sg = g_stats + (rb * 8 + warp) * 512 + g * 4;
    uint32_t* sp[4];
#pragma unroll
    for (int k = 0; k < 4; k++) sp[k] = sg + (tq & 1) * 32 + (((tq >> 1) ^ (cj >> 2)) * 4 + (k ^ (cj & 3))) * 64;
    {
      const uint64_t da = make_desc(base + wg * 8192, 16, 1024), db = make_desc(base, 8192, 1024);
      constexpr int U = UNIT / 16;
#define HALF_STAGE(acc, xu, wu) _Pragma("unroll") for (int kk = 0; kk < 4; kk++) mma_ss<1>(acc, da + (xu) * U + kk * 2, db + (wu) * U + kk * 128, 1)
      PROF(10, ct == PT, 19); STAMP(0);
      cluster_arrive();
      mbar_wait(gfull, 1);
      mbar_wait(gfull + 8, 1);
      bar_sync(2 + wg, 256);
      wg_fence();
      HALF_STAGE(o, 7, 1);
      HALF_STAGE(o, 8, 3);
      wg_commit();
      STAMP(16);
      mbar_wait(gfull + 16, 1);
      STAMP(17);
      wg_fence();
      HALF_STAGE(o, 6, 11);
      wg_commit();
      bar_arrive(3 - wg, 256);
      mbar_wait(bar_par, 0);
      uint32_t* xo = g_xch + ((size_t)b * 8 * 256 + ct) * 4;
      const uint32_t* xi = g_xch + ((size_t)(b ^ 2) * 8 * 256 + ct) * 4;
      const uint32_t par1 = (~lds1(par + PAR_CONST + 4) & 1) << 16;
      wg_wait<1>();
      mbar_arrive_pred(bar_rel, lane0);
      wg_wait<0>();
      keep(o);
      mbar_arrive_pred(bar_ring, lane0);
      PROF(8, ct == PT, 20); STAMP(1);
#define SEND(i) st_b128(xo + (i) * 1024, (pack_bf(o[8 * (i)], o[8 * (i) + 1]) & ~0x10000u) | par1, pack_bf(o[8 * (i) + 2], o[8 * (i) + 3]), \
                        pack_bf(o[8 * (i) + 4], o[8 * (i) + 5]), pack_bf(o[8 * (i) + 6], o[8 * (i) + 7]))
#pragma unroll
      for (int i = 0; i < NS1; i++) SEND(i);
      PROF(8, ct == PT, 21); STAMP(2);
      bar_sync(2 + wg, 256);
      wg_fence();
      HALF_STAGE(s, 7, 0);
      HALF_STAGE(s, 8, 2);
      HALF_STAGE(s, 6, 10);
      wg_commit();
      bar_arrive(3 - wg, 256);
      STAMP(18);
      mbar_wait(gfull + 24, 1);
#pragma unroll
      for (int i = NS1; i < 8; i++) SEND(i);
      uint4 v[8];
      STAMP(19);
      mbar_wait(bar_xres, 0);
      wg_wait<0>();
      mbar_arrive_pred(bar_ring + 8, lane0);
      bar_sync(2 + wg, 256);
      STAMP(20);
#pragma unroll
      for (int i = 0; i < LD2; i++) v[i] = ld_b128(xi + i * 1024);
      mbar_wait(bar_xres, 0);
      wg_fence();
      HALF_STAGE(s, 9, 4);
      wg_commit();
      mbar_wait(bar_rx, 0);
      wg_fence();
      HALF_STAGE(s, 1, 5);
      wg_commit();
      bar_arrive(3 - wg, 256);
      STAMP(21);
#pragma unroll
      for (int i = LD2; i < 8; i++) v[i] = ld_b128(xi + i * 1024);
      mbar_wait(bar_xres, 0);
      wg_wait<0>();
      keep(s);
      mbar_arrive_pred(bar_ring + 16, lane0);
      PROF(10, ct == PT, 23); STAMP(4);
#pragma unroll
      for (int i = 0; i < 16; i += 2) ldmatrix4((trow ^ ((i & 7) << 4)) + (i >> 3) * 16384, xr[2 * i], xr[2 * i + 1], xr[2 * i + 2], xr[2 * i + 3]);
      uint32_t ga[16];
      uint4 bw[8];
#pragma unroll
      for (int i = 0; i < 8; i++) {
        if (!(i & 1)) {
          const uint4 t = lds4(par + PAR_SINK + i * 32 + tq * 16);
          ga[2 * i] = t.x; ga[2 * i + 1] = t.y; ga[2 * i + 2] = t.z; ga[2 * i + 3] = t.w;
        }
        bw[i] = lds4(par + PAR_T1 + i * 64 + tq * 16);
        if (!(g & 1)) { bw[i].x = 0x3f803f80u; bw[i].y = 0x3f803f80u; }
      }
      uint32_t pk[32];
      pack_p(s, pk);
      const uint32_t par2 = (~lds1(par + PAR_CONST + 12) & 1) << 16;
      {
        uint32_t n = 0, miss;
        do {
          miss = 0;
#pragma unroll
          for (int i = 0; i < 8; i++) miss |= v[i].x ^ par2;
          miss = __any_sync(0xffffffffu, miss & 0x10000u);
          if (miss) {
#pragma unroll
            for (int i = 0; i < 8; i++)
              asm volatile("{ .reg .pred p; .reg .b32 t; xor.b32 t, %0, %5; and.b32 t, t, 0x10000; setp.ne.u32 p, t, 0;\n"
                           "@p ld.relaxed.gpu.global.v4.u32 {%0, %1, %2, %3}, [%4]; }"
                           : "+r"(v[i].x), "+r"(v[i].y), "+r"(v[i].z), "+r"(v[i].w) : "l"(xi + i * 1024), "r"(par1) : "memory");
          }
          watchdog(n);
        } while (miss);
      }
      PROF(8, ct == PT, 22); STAMP(3);
      float ds[4] = {0.f, 0.f, 0.f, 0.f}, dl[4] = {0.f, 0.f, 0.f, 0.f}, q0[4] = {0.f, 0.f, 0.f, 0.f}, q1[4] = {0.f, 0.f, 0.f, 0.f};
#pragma unroll
      for (int i = 0; i < 8; i++) {
        const uint32_t u0 = hfma2(ga[2 * i], hadd2(pk[4 * i], v[i].x & ~0x10000u), xr[4 * i]);
        const uint32_t u1 = hfma2(ga[2 * i], hadd2(pk[4 * i + 1], v[i].y), xr[4 * i + 1]);
        const uint32_t u2 = hfma2(ga[2 * i + 1], hadd2(pk[4 * i + 2], v[i].z), xr[4 * i + 2]);
        const uint32_t u3 = hfma2(ga[2 * i + 1], hadd2(pk[4 * i + 3], v[i].w), xr[4 * i + 3]);
        xr[4 * i] = u0; xr[4 * i + 1] = u1; xr[4 * i + 2] = u2; xr[4 * i + 3] = u3;
        mma16816(ds, u0, u1, u2, u3, bw[i].x, bw[i].y);
        mma16816(dl, u0, u1, u2, u3, bw[i].z, bw[i].w);
        mma16816(q0, u0, u1, u2, u3, u0, u2);
        mma16816(q1, u0, u1, u2, u3, u1, u3);
      }
      const float sqa = (g & 1) ? q0[1] : q0[0], sqb = (g & 1) ? q1[3] : q1[2], dta = ds[1] + dl[1], dtb = ds[3] + dl[3];
      if (tq == (g >> 1)) {
        st_b128(sg + cj * 64, __float_as_uint(ds[0]), __float_as_uint(sqa), __float_as_uint(dta), tag);
        st_b128(sg + cj * 64 + 32, __float_as_uint(ds[2]), __float_as_uint(sqb), __float_as_uint(dtb), tag);
      }
#pragma unroll
      for (int k = 0; k < 4; k++) sv[k] = ld_b128(sp[k]);
      mbar_wait(bar_xres, 0);
      const float sqc = __shfl_sync(0xffffffffu, sqa, g * 4 + (g >> 1)), sqd = __shfl_sync(0xffffffffu, sqb, g * 4 + (g >> 1));
      own = (tq & 1) ? make_uint4(__float_as_uint(ds[2]), __float_as_uint(sqd), __float_as_uint(dtb), tag)
                     : make_uint4(__float_as_uint(ds[0]), __float_as_uint(sqc), __float_as_uint(dta), tag);
    }
    PROF(8, ct == PT, 29); STAMP(5);
    uint32_t mm, ih, il;
    float rbest;
    uint32_t wf[128];
    const uint32_t frow = (ln & 7) + (ln >> 4) * 8;
    const uint32_t wfo = base + (warp & 1) * 8192 + frow * 64 + ((((ln >> 3) & 1) ^ ((frow >> 1) & 3)) << 4);
#define LOAD_WF(m) _Pragma("unroll") for (int f = 0; f < 16; f++) {                                                   \
      const int r = ((f >> 1) * 4 + (m) * 2 + (f & 1)) * 4;                                                           \
      ldmatrix4t(((wfo + unit_of((m) ? FT_U : FT_G, warp >> 1)) ^ ((f & 1) * 32)) + (f >> 1) * 1024, wf[r], wf[r + 1], wf[r + 2], wf[r + 3]); \
    }
    bool early;
    {
#pragma unroll
      for (int i = 0; i < 16; i += 2) stmatrix4((trow ^ ((i & 7) << 4)) + (i >> 3) * 16384, xr[2 * i], xr[2 * i + 1], xr[2 * i + 2], xr[2 * i + 3]);
      const uint4 cst = lds4(par + PAR_CONST);
      const float A1 = __uint_as_float(cst.x), A2 = __uint_as_float(cst.z);
      uint32_t n = 0;
      early = false;
#pragma unroll 1
      while (true) {
        if (!early && (b >= NFFN || __all_sync(0xffffffffu, mbar_test(bar_box + (warp >> 1) * 8, 0)))) {
          early = true;
          LOAD_WF(0);
          __syncwarp();
          mbar_arrive_pred(bar_gate, lane0);
        }
        uint32_t miss;
        asm volatile("{ .reg .pred p0, p1, p2, p3; .reg .b64 u, v; .reg .b128 w;\n"
                     "setp.ge.u32 p0, %22, 2; setp.ne.and.u32 p0, %4, %21, p0; setp.ne.u32 p1, %8, %21; setp.ne.u32 p2, %12, %21; setp.ne.u32 p3, %16, %21;\n"
                     "@p0 ld.relaxed.gpu.global.v4.u32 {%1, %2, %3, %4}, [%17];\n"
                     "@p1 ld.relaxed.gpu.global.v4.u32 {%5, %6, %7, %8}, [%18];\n"
                     "@p2 ld.relaxed.gpu.global.v4.u32 {%9, %10, %11, %12}, [%19];\n"
                     "@p3 ld.relaxed.gpu.global.v4.u32 {%13, %14, %15, %16}, [%20];\n"
                     "or.pred p0, p0, p1; or.pred p2, p2, p3; or.pred p0, p0, p2; vote.sync.any.pred p0, p0, 0xffffffff; selp.u32 %0, 1, 0, p0; }"
                     : "=r"(miss), "+r"(sv[0].x), "+r"(sv[0].y), "+r"(sv[0].z), "+r"(sv[0].w), "+r"(sv[1].x), "+r"(sv[1].y), "+r"(sv[1].z), "+r"(sv[1].w),
                       "+r"(sv[2].x), "+r"(sv[2].y), "+r"(sv[2].z), "+r"(sv[2].w), "+r"(sv[3].x), "+r"(sv[3].y), "+r"(sv[3].z), "+r"(sv[3].w)
                     : "l"(sp[0]), "l"(sp[1]), "l"(sp[2]), "l"(sp[3]), "r"(tag), "r"(tq) : "memory");
        if (!miss) break;
        watchdog(n);
      }
      const uint4 v0 = tq < 2 ? own : sv[0], v1 = sv[1], v2 = sv[2], v3 = sv[3];
      PROF(8, ct == PT, 30); STAMP(6);
      float su = (__uint_as_float(v0.x) + __uint_as_float(v1.x)) + (__uint_as_float(v2.x) + __uint_as_float(v3.x));
      float sq = (__uint_as_float(v0.y) + __uint_as_float(v1.y)) + (__uint_as_float(v2.y) + __uint_as_float(v3.y));
      float dt = (__uint_as_float(v0.z) + __uint_as_float(v1.z)) + (__uint_as_float(v2.z) + __uint_as_float(v3.z));
      su += __shfl_xor_sync(0xffffffffu, su, 2); sq += __shfl_xor_sync(0xffffffffu, sq, 2); dt += __shfl_xor_sync(0xffffffffu, dt, 2);
      const float m = su * (1.f / DM);
      float mb, sd;
      ln_scalars(m, fmaxf(sq * (1.f / DM) - m * m, 0.f), mb, sd);
      const float inv = rcp(sd);
      rbest = (dt - mb * A1) * inv + A2;
      mm = pack_bf(mb, mb);
      ih = pack_bf(inv, inv);
      const float lo = inv - bf_lo(ih);
      il = pack_bf(lo, lo);
    }
    int ibest;
    {
      const uint32_t bits = __float_as_uint(rbest);
      const uint32_t key = (((int)bits < 0 ? ~bits : bits | 0x80000000u) & ~0x1ffu) | ((127 - lrow0 - (tq & 1) * 8) << 2) | tag;
      sts1(par + PAR_RED + warp * 4, __reduce_max_sync(0xffffffffu, key));
      PROF(8, ct == PT, 38); STAMP(7);
      bar_sync(1, 256);
      const uint4 ka = lds4(par + PAR_RED), kb = lds4(par + PAR_RED + 16);
      const uint32_t k2 = max(max(max(ka.x, ka.y), max(ka.z, ka.w)), max(max(kb.x, kb.y), max(kb.z, kb.w)));
      if (ct < CR && cj == 0) st_relaxed(g_cand + ct * 512 + rb * CS, k2);
      ibest = 127 - ((k2 >> 2) & 127);
    }
    PROF(8, ct == PT, 39); STAMP(8);
    if ((ibest >> 4) == warp) {
      const int src = (ibest & 7) * 4 + ((ibest >> 3) & 1), ch = g * 2;
      const uint32_t cm = __shfl_sync(0xffffffffu, mm, src), ch_ = __shfl_sync(0xffffffffu, ih, src), cl = __shfl_sync(0xffffffffu, il, src);
      const uint32_t xa = res + (ch >> 3) * 16384 + ibest * 128 + (((ch & 7) ^ (ibest & 7)) << 4) + tq * 4;
      const uint32_t x0 = lds1(xa), x1 = lds1(xa ^ 16);
      const uint2 p0 = lds2(par + PAR_T2 + ch * 64 + tq * 16), p1 = lds2(par + PAR_T2 + ch * 64 + 64 + tq * 16);
      uint32_t* dst = g_row + rb * 2 * DM + cj * 128 + ln * 4;
      st_pairs(dst, ln_mod(x0, cm, ch_, cl, p0.x, p0.y), ln_mod(x1, cm, ch_, cl, p1.x, p1.y), tag);
      st_pairs(dst + DM, x0, x1, tag);
      __syncwarp();
    }
    PROF(8, ct == PT, 37); STAMP(9);
    uint32_t wd[64];
    const uint32_t wda = base + unit_of(FT_D, warp >> 1) + (warp & 1) * 8192 + frow * 128 + ((((ln >> 3) & 1) ^ (ln & 7)) << 4);
#define LOAD_WD(f) ldmatrix4t((wda ^ ((((f) >> 1) & 3) * 32)) + ((f) >> 3) * 4096 + ((f) & 1) * 2048, wd[4 * (f)], wd[4 * (f) + 1], wd[4 * (f) + 2], wd[4 * (f) + 3])
    if (!early) {
      if (b < NFFN) mbar_wait(bar_box + (warp >> 1) * 8, 0);
      LOAD_WF(0);
      __syncwarp();
      mbar_arrive_pred(bar_gate, lane0);
    }
    if (b < NFFN) {
      const uint32_t own = base + unit_of(FT_G, warp >> 1) + (warp & 1) * 8192;
      mbar_wait(bar_box + (4 + (warp >> 1)) * 8, 0);
      LOAD_WF(1);
      uint32_t* const ydst = ypart_slot(b, warp * 16 + (tq & 1) * 8 + g);
      PROF(8, ct == PT, 31); STAMP(10);
      bool wdok;
      {
        uint32_t n = 0;
        while (!(wdok = __all_sync(0xffffffffu, mbar_test(bar_box + (8 + (warp >> 1)) * 8, 0))) && !__all_sync(0xffffffffu, mbar_test(bar_sel, 0))) watchdog(n);
      }
      if (wdok) {
#pragma unroll
        for (int f = 0; f < 16; f++) LOAD_WD(f);
      }
      STAMP(11);
      mbar_wait(bar_sel, 0);
      PROF(8, ct == PT, 33); STAMP(12);
      float d[8][4];
#pragma unroll
      for (int i = 0; i < 4; i++) { d[i][0] = 0.f; d[i][1] = 0.f; d[i][2] = 0.f; d[i][3] = 0.f; }
#pragma unroll
      for (int ks = 0; ks < 8; ks++) {
        const uint2 hb = lds2(own + 256 + ks * 32 + tq * 8);
#pragma unroll
        for (int mt = 0; mt < 4; mt++) {
          const int r = ks * 16 + mt * 4;
          mma16816(d[mt], wf[r], wf[r + 1], wf[r + 2], wf[r + 3], hb.x, hb.y);
        }
      }
      sts2(own + (tq * 8 + g) * 8, __float_as_uint((tq & 2) ? ((tq & 1) ? d[1][2] : d[1][0]) : ((tq & 1) ? d[0][2] : d[0][0])),
           __float_as_uint((tq & 2) ? ((tq & 1) ? d[3][2] : d[3][0]) : ((tq & 1) ? d[2][2] : d[2][0])));
      bar_sync(1, 256);
      uint32_t ab[4];
      {
        float G = 0.f, U = 0.f;
        uint2 pv[8];
#pragma unroll
        for (int w8 = 0; w8 < 8; w8++) pv[w8] = lds2(base + ln * 8 + ((FT_G >> (w8 >> 1) * 4) & 15) * UNIT + (w8 & 1) * 8192);
#pragma unroll
        for (int w8 = 0; w8 < 8; w8 += 2) {
          G += __uint_as_float(pv[w8].x) + __uint_as_float(pv[w8 + 1].x);
          U += __uint_as_float(pv[w8].y) + __uint_as_float(pv[w8 + 1].y);
        }
        const float act = rbf(silu_f(rbf(G))) * rbf(U);
        const uint32_t pk = pack_bf(act, __shfl_down_sync(0xffffffffu, act, 1));
#pragma unroll
        for (int i = 0; i < 4; i++) ab[i] = __shfl_sync(0xffffffffu, pk, i * 8 + tq * 2);
      }
      if (!wdok) {
        mbar_wait(bar_box + (8 + (warp >> 1)) * 8, 0);
#pragma unroll
        for (int f = 0; f < 16; f++) LOAD_WD(f);
      }
      PROF(8, ct == PT, 34); STAMP(13);
#pragma unroll
      for (int mt = 0; mt < 8; mt++) {
        d[mt][0] = 0.f; d[mt][1] = 0.f; d[mt][2] = 0.f; d[mt][3] = 0.f;
        mma16816(d[mt], wd[mt * 8], wd[mt * 8 + 1], wd[mt * 8 + 2], wd[mt * 8 + 3], ab[0], ab[1]);
        mma16816(d[mt], wd[mt * 8 + 4], wd[mt * 8 + 5], wd[mt * 8 + 6], wd[mt * 8 + 7], ab[2], ab[3]);
      }
      uint32_t yw[4];
#pragma unroll
      for (int i = 0; i < 4; i++) yw[i] = (tq & 1) ? pack_bf(d[2 * i][2], d[2 * i + 1][2]) : pack_bf(d[2 * i][0], d[2 * i + 1][0]);
      if (tq < 2) st_b128(ydst, (yw[0] & ~1u) | (tag & 1), (yw[1] & ~1u) | (tag >> 1), yw[2], yw[3]);
      PROF(8, ct == PT, 35); STAMP(14);
    }
    mbar_wait(bar_sel, 0);
    mbar_arrive_pred(bar_win, ct == 0);
    const int iwin = lds1(par + PAR_CONST + 60) & 0x7ff;
    const bool cand = (iwin >> 4) == rb * 8 + warp;
    {
      const uint32_t mm0 = __shfl_sync(0xffffffffu, mm, ln & ~1), mm1 = __shfl_sync(0xffffffffu, mm, ln | 1);
      const uint32_t ih0 = __shfl_sync(0xffffffffu, ih, ln & ~1), ih1 = __shfl_sync(0xffffffffu, ih, ln | 1);
      const uint32_t il0 = __shfl_sync(0xffffffffu, il, ln & ~1), il1 = __shfl_sync(0xffffffffu, il, ln | 1);
#pragma unroll 1
      for (int hf = 0; hf < 2; hf++) {
        uint32_t x[16];
#pragma unroll
        for (int i = 0; i < 8; i += 2) ldmatrix4((trow ^ (i << 4)) + hf * 16384, x[2 * i], x[2 * i + 1], x[2 * i + 2], x[2 * i + 3]);
#pragma unroll
        for (int i = 0; i < 8; i++) {
          const uint4 pv = lds4(par + PAR_T2 + (hf * 8 + i) * 64 + tq * 16);
          x[2 * i] = hfma2(hfma2(ln_norm(x[2 * i], mm0, ih0, il0), pv.x, pv.y), pv.z, x[2 * i]);
          x[2 * i + 1] = hfma2(hfma2(ln_norm(x[2 * i + 1], mm1, ih1, il1), pv.x, pv.y), pv.z, x[2 * i + 1]);
        }
#pragma unroll
        for (int i = 0; i < 8; i += 2) stmatrix4((trow ^ (i << 4)) + hf * 16384, x[2 * i], x[2 * i + 1], x[2 * i + 2], x[2 * i + 3]);
        if (!cand) fence_async_smem();
        __syncwarp();
        if (!cand && elect_one()) {
          tma2d_store(&maps.out, res + hf * 16384 + warp * 2048, cj * 128 + hf * 64, rb * 128 + warp * 16);
          asm volatile("cp.async.bulk.commit_group;" ::: "memory");
        }
      }
    }
    if (cand) {
      const int wrow0 = warp * 16;
#pragma unroll 2
      for (int p = 0; p < 8; p++) {
        const int row = 2 * p + (ln >> 4), ch = ln & 15;
        const uint4 v = lds4(res + (ch >> 3) * 16384 + (wrow0 + row) * 128 + (((ch & 7) ^ (row & 7)) << 4));
        if (rb * 128 + wrow0 + row != iwin) *reinterpret_cast<uint4*>(P.out + (size_t)(rb * 128 + wrow0 + row) * DM + cj * 128 + ch * 8) = v;
      }
    }
    asm volatile("cp.async.bulk.wait_group.read 0;" ::: "memory");
    PROF(8, ct == PT, 11); STAMP(15);
    cluster_wait();
  }
}

typedef CUresult (*EncodeFn)(CUtensorMap*, CUtensorMapDataType, cuuint32_t, void*, const cuuint64_t*, const cuuint64_t*,
                             const cuuint32_t*, const cuuint32_t*, CUtensorMapInterleave, CUtensorMapSwizzle,
                             CUtensorMapL2promotion, CUtensorMapFloatOOBfill);

void map2d(EncodeFn enc, CUtensorMap* m, const void* p, uint64_t rows, uint64_t cols, uint32_t brows) {
  cuuint64_t dims[2] = {cols, rows}, strides[1] = {cols * 2};
  cuuint32_t box[2] = {64, brows}, es[2] = {1, 1};
  enc(m, CU_TENSOR_MAP_DATA_TYPE_BFLOAT16, 2, const_cast<void*>(p), dims, strides, box, es, CU_TENSOR_MAP_INTERLEAVE_NONE,
      CU_TENSOR_MAP_SWIZZLE_128B, CU_TENSOR_MAP_L2_PROMOTION_L2_256B, CU_TENSOR_MAP_FLOAT_OOB_FILL_NONE);
}
void map2d_narrow(EncodeFn enc, CUtensorMap* m, const void* p, uint64_t rows, uint64_t cols, uint32_t brows) {
  cuuint64_t dims[2] = {cols, rows}, strides[1] = {cols * 2};
  cuuint32_t box[2] = {32, brows}, es[2] = {1, 1};
  enc(m, CU_TENSOR_MAP_DATA_TYPE_BFLOAT16, 2, const_cast<void*>(p), dims, strides, box, es, CU_TENSOR_MAP_INTERLEAVE_NONE,
      CU_TENSOR_MAP_SWIZZLE_64B, CU_TENSOR_MAP_L2_PROMOTION_L2_64B, CU_TENSOR_MAP_FLOAT_OOB_FILL_NONE);
}
void map3d(EncodeFn enc, CUtensorMap* m, const void* p, uint64_t rows, uint64_t cols, uint32_t brows, uint32_t nch) {
  cuuint64_t dims[3] = {64, rows, cols / 64}, strides[2] = {cols * 2, 128};
  cuuint32_t box[3] = {64, brows, nch}, es[3] = {1, 1, 1};
  enc(m, CU_TENSOR_MAP_DATA_TYPE_BFLOAT16, 3, const_cast<void*>(p), dims, strides, box, es, CU_TENSOR_MAP_INTERLEAVE_NONE,
      CU_TENSOR_MAP_SWIZZLE_128B, CU_TENSOR_MAP_L2_PROMOTION_L2_256B, CU_TENSOR_MAP_FLOAT_OOB_FILL_NONE);
}

}

extern "C" void kernel_launch(void* const* d_in, const int* in_sizes, int n_in, void* d_out, int out_size) {
  (void)in_sizes; (void)n_in; (void)out_size;
  static EncodeFn enc = nullptr;
  if (!enc) {
    void* fn = nullptr;
    cudaDriverEntryPointQueryResult st;
    cudaGetDriverEntryPoint("cuTensorMapEncodeTiled", &fn, cudaEnableDefault, &st);
    enc = (EncodeFn)fn;
    cudaFuncSetAttribute(fused_kernel, cudaFuncAttributeMaxDynamicSharedMemorySize, SMEM_BYTES);
  }
  Maps maps;
  map2d(enc, &maps.x, d_in[0], SEQ, DM, 128);
  map2d(enc, &maps.out, d_out, SEQ, DM, 16);
  map3d(enc, &maps.wq, d_in[3], DM, NQ, 64, 2);
  map3d(enc, &maps.k, d_in[1], 4 * SK, 128, 128, 1);
  map3d(enc, &maps.v, d_in[2], 4 * SK, 128, 128, 1);
  map3d(enc, &maps.wo, d_in[4], NQ, DM, 64, 2);
  map2d_narrow(enc, &maps.wg, d_in[7], DM, FF, 256);
  map2d_narrow(enc, &maps.wu, d_in[8], DM, FF, 256);
  map3d(enc, &maps.wd, d_in[9], FF, DM, 32, 4);
  map2d_narrow(enc, &maps.wm, d_in[11], DM, NMOD, 256);
  Ptrs p;
  p.x = (const __nv_bfloat16*)d_in[0];
  p.w_r = (const __nv_bfloat16*)d_in[6];
  p.w_gate = (const __nv_bfloat16*)d_in[7];
  p.w_up = (const __nv_bfloat16*)d_in[8];
  p.w_down = (const __nv_bfloat16*)d_in[9];
  p.c = (const __nv_bfloat16*)d_in[10];
  p.w_mod = (const __nv_bfloat16*)d_in[11];
  p.out = (__nv_bfloat16*)d_out;
  fused_kernel<<<NMAIN + NHELP, 384, SMEM_BYTES>>>(maps, p);
}
```

```cpp
#include <cuda_runtime.h>
#include <cuda_bf16.h>
#include <cuda.h>
#include <stdint.h>
#include <type_traits>

#define HD 2
#define HDX 2
#define NRS 8
#define OSL 900
#define OSL2 400
#define RSL 40
#define XN 0
#define KP 0
#define VREL 5
#define OPS 8192
#define ODS1 5
#define ODS 7
#define PG0 15
#define WB 2
#define WN 20
#define HU 32
#define RES0 17
#define RES1 20
#define GOST 20
#define NS1 5
#define LD2 4
#define FPACE0 2
#define FPACE 3
#define CR 8
#define CS 8

namespace {

constexpr int SEQ = 2048, DM = 1024, NQ = 4096, SK = 2048, WIN = 512, FF = 3584, NMOD = 6144;
constexpr int NMAIN = 128, NHELP = 4, NFFN = 112;
constexpr int NSLOT = 4, SLOT_BYTES = 32768, UNIT = 16384, GST_BYTES = 3 * UNIT;
constexpr uint32_t XT1 = 0xDCBA, XT2 = 0x9687, XT2B = 0x96DC;
constexpr uint32_t WT0 = 0xA741, WT1 = 0x7420, WT2 = 0x4A20;
constexpr uint32_t AT0 = WT1, AT1 = WT2;
constexpr uint32_t QT = 0xDC9696DC;
constexpr int OFF_STAGE = 12 * UNIT;
constexpr uint32_t FT_G = 0x07B3, FT_U = 0xA628, FT_D = 0x5149;
constexpr int OFF_RES = 12 * UNIT;
constexpr int OFF_PAR = 14 * UNIT;
constexpr int OFF_BAR = OFF_PAR + 2528;
constexpr int SMEM_BYTES = OFF_BAR + 544;
static_assert(SMEM_BYTES <= 232448, "smem");

constexpr int PAR_T1 = 0;
constexpr int PAR_T2 = 512;
constexpr int PAR_CONST = 1536;
constexpr int PAR_RED = 1600;
constexpr int PAR_SINK = 2176;

struct Maps {
  CUtensorMap x, wq, k, v, wo, wg, wu, wd, wm, out;
};
struct Ptrs {
  const __nv_bfloat16 *x, *w_r, *c, *w_mod, *w_gate, *w_up, *w_down;
  __nv_bfloat16* out;
};

__device__ __align__(1024) uint8_t g_act[16 * 80 * UNIT];
__device__ __align__(128) uint32_t g_mod[NMOD];
__device__ __align__(128) uint32_t g_modp[2 * 2 * DM];
__device__ __align__(128) uint32_t g_ln1[SEQ * 4];
__device__ __align__(128) uint32_t g_cnt_h[16 * 32];
__device__ __align__(128) uint32_t g_cnt_o[128 * 32];
__device__ __align__(128) uint32_t g_xch[NMAIN * 8 * 256 * 4];
__device__ __align__(128) uint32_t g_stats[8 * SEQ * 4];
__device__ __align__(128) uint32_t g_cand[CR * 512];
__device__ __align__(128) uint32_t g_row[16 * 2 * DM];
__device__ __align__(128) uint32_t g_ypart[NMAIN * NFFN * 4];
__device__ __forceinline__ uint32_t* ypart_slot(int writer, int reader) { return g_ypart + (writer * NMAIN + reader) * 4; }
__device__ uint32_t g_epoch;

__device__ __forceinline__ uint32_t fresh_lane() { uint32_t l; asm volatile("mov.u32 %0, %%laneid;" : "=r"(l)); return l; }
__device__ __forceinline__ uint32_t frag_offset(int warp) {
  const uint32_t l = fresh_lane();
  return ((warp & 3) * 16 + (l & 15)) * 128 + (((l >> 4) ^ (l & 7)) << 4);
}
__device__ __forceinline__ bool elect_one() {
  uint32_t p;
  asm volatile("{ .reg .pred q; elect.sync _|q, 0xffffffff; selp.u32 %0, 1, 0, q; }" : "=r"(p));
  return p;
}
__device__ __forceinline__ uint32_t smem_u32(const void* p) { return (uint32_t)__cvta_generic_to_shared(p); }
__device__ __forceinline__ void mbar_init(uint32_t bar, uint32_t cnt) {
  asm volatile("mbarrier.init.shared::cta.b64 [%0], %1;" ::"r"(bar), "r"(cnt) : "memory");
}
__device__ __forceinline__ void mbar_expect_tx(uint32_t bar, uint32_t bytes) {
  asm volatile("mbarrier.arrive.expect_tx.shared::cta.b64 _, [%0], %1;" ::"r"(bar), "r"(bytes) : "memory");
}
__device__ __forceinline__ void mbar_arrive(uint32_t bar) {
  asm volatile("mbarrier.arrive.shared::cta.b64 _, [%0];" ::"r"(bar) : "memory");
}
__device__ __forceinline__ void mbar_arrive_pred(uint32_t bar, bool p) {
  asm volatile("{ .reg .pred p; setp.ne.b32 p, %1, 0; @p mbarrier.arrive.shared::cta.b64 _, [%0]; }" ::"r"(bar), "r"((int)p) : "memory");
}
__device__ __forceinline__ void mbar_arrive_cl(uint32_t bar, uint32_t off, bool p = true) {
  asm volatile("{ .reg .pred p, q; .reg .b32 a; setp.ne.b32 q, %2, 0; setp.ne.and.b32 p, %0, 0, q; add.u32 a, %0, %1; @p mbarrier.arrive.shared::cluster.b64 _, [a]; }"
               ::"r"(bar), "r"(off), "r"((int)p) : "memory");
}
__device__ __forceinline__ uint32_t mapa(uint32_t addr, uint32_t cta) {
  uint32_t r; asm("mapa.shared::cluster.u32 %0, %1, %2;" : "=r"(r) : "r"(addr), "r"(cta)); return r;
}
__device__ __forceinline__ void cluster_arrive() { asm volatile("barrier.cluster.arrive.relaxed.aligned;" ::: "memory"); }
__device__ __forceinline__ void cluster_wait() { asm volatile("barrier.cluster.wait.aligned;" ::: "memory"); }
__device__ __forceinline__ void watchdog(uint32_t& n) {
}
__device__ __forceinline__ void mbar_wait(uint32_t bar, uint32_t parity) {
  asm volatile("{\n.reg .pred p;\nWAIT_%=:\nmbarrier.try_wait.parity.shared::cta.b64 p, [%0], %1;\n@!p bra WAIT_%=;\n}" ::"r"(bar), "r"(parity) : "memory");
}
__device__ __forceinline__ bool mbar_test(uint32_t bar, uint32_t parity) {
  uint32_t ok;
  asm volatile("{\n.reg .pred p;\nmbarrier.test_wait.parity.shared::cta.b64 p, [%1], %2;\nselp.u32 %0, 1, 0, p;\n}" : "=r"(ok) : "r"(bar), "r"(parity) : "memory");
  return ok;
}
__device__ __forceinline__ uint64_t l2_stream() {
  uint64_t f; asm("createpolicy.fractional.L2::evict_first.b64 %0, 1.0;" : "=l"(f)); return f;
}
__device__ __forceinline__ uint64_t l2_normal() {
  uint64_t f; asm("createpolicy.fractional.L2::evict_normal.b64 %0, 1.0;" : "=l"(f)); return f;
}
__device__ __forceinline__ void tma2d(uint32_t dst, const CUtensorMap* m, int c0, int c1, uint32_t bar) {
  asm volatile("cp.async.bulk.tensor.2d.shared::cluster.global.mbarrier::complete_tx::bytes.L2::cache_hint [%0], [%1, {%3, %4}], [%2], %5;"
               ::"r"(dst), "l"(m), "r"(bar), "r"(c0), "r"(c1), "l"(l2_stream()) : "memory");
}
__device__ __forceinline__ void bulk_load(uint32_t dst, const void* src, uint32_t bytes, uint32_t bar) {
  asm volatile("cp.async.bulk.shared::cluster.global.mbarrier::complete_tx::bytes [%0], [%1], %2, [%3];" ::"r"(dst), "l"(src), "r"(bytes), "r"(bar) : "memory");
}
__device__ __forceinline__ void bulk_load_stream(uint32_t dst, const void* src, uint32_t bytes, uint32_t bar, uint64_t pol = l2_stream()) {
  asm volatile("cp.async.bulk.shared::cluster.global.mbarrier::complete_tx::bytes.L2::cache_hint [%0], [%1], %2, [%3], %4;"
               ::"r"(dst), "l"(src), "r"(bytes), "r"(bar), "l"(pol) : "memory");
}
__device__ __forceinline__ void tma2d_store(const CUtensorMap* m, uint32_t src, int c0, int c1) {
  asm volatile("cp.async.bulk.tensor.2d.global.shared::cta.bulk_group [%0, {%2, %3}], [%1];" ::"l"(m), "r"(src), "r"(c0), "r"(c1) : "memory");
}
__device__ __forceinline__ void bulk_store(void* dst, uint32_t src, uint32_t bytes) {
  asm volatile("cp.async.bulk.global.shared::cta.bulk_group [%0], [%1], %2;" ::"l"(dst), "r"(src), "r"(bytes) : "memory");
}
__device__ __forceinline__ int slice_of(int i) { return i + ((i & 7) == 1) - ((i & 7) == 2); }
__device__ __forceinline__ int otile_of(int i, int cj) {
  const int h = (0xFB7EA6D951C84320ull >> (i >> 1) * 4) & 15, r = h >> 2, a0 = cj >> 1;
  const int a = (h & 2) ? (r ? r - (r <= a0) : a0) : r;
  return ((2 * a + (cj & 1)) * 4 + (h & 3)) * 2 + (i & 1);
}
__device__ __forceinline__ uint32_t unit_of(uint32_t table, uint32_t i) { return ((table >> (i * 4)) & 15) * UNIT; }
__device__ __forceinline__ void tma3d(uint32_t dst, const CUtensorMap* m, int c0, int c1, int c2, uint32_t bar) {
  asm volatile("cp.async.bulk.tensor.3d.shared::cluster.global.mbarrier::complete_tx::bytes.L2::cache_hint [%0], [%1, {%3, %4, %5}], [%2], %6;"
               ::"r"(dst), "l"(m), "r"(bar), "r"(c0), "r"(c1), "r"(c2), "l"(l2_stream()) : "memory");
}
template <bool STREAM>
__device__ __forceinline__ void tma3d_mc(uint32_t dst, const CUtensorMap* m, int c0, int c1, int c2, uint32_t bar) {
  if (STREAM)
    asm volatile("cp.async.bulk.tensor.3d.shared::cluster.global.mbarrier::complete_tx::bytes.multicast::cluster.L2::cache_hint [%0], [%1, {%3, %4, %5}], [%2], %6, %7;"
                 ::"r"(dst), "l"(m), "r"(bar), "r"(c0), "r"(c1), "r"(c2), "h"((uint16_t)3), "l"(l2_stream()) : "memory");
  else
    asm volatile("cp.async.bulk.tensor.3d.shared::cluster.global.mbarrier::complete_tx::bytes.multicast::cluster [%0], [%1, {%3, %4, %5}], [%2], %6;"
                 ::"r"(dst), "l"(m), "r"(bar), "r"(c0), "r"(c1), "r"(c2), "h"((uint16_t)3) : "memory");
}
__device__ __forceinline__ void prefetch_map(const CUtensorMap* m) {
  asm volatile("prefetch.tensormap [%0];" ::"l"(m) : "memory");
}
__device__ __forceinline__ void fence_async() { asm volatile("fence.proxy.async.global;" ::: "memory"); }
__device__ __forceinline__ void fence_async_smem() { asm volatile("fence.proxy.async.shared::cta;" ::: "memory"); }
__device__ __forceinline__ void bar_sync(int id, int n) { asm volatile("bar.sync %0, %1;" ::"r"(id), "r"(n) : "memory"); }
__device__ __forceinline__ void bar_arrive(int id, int n) { asm volatile("bar.arrive %0, %1;" ::"r"(id), "r"(n) : "memory"); }
__device__ __forceinline__ void wg_fence() { asm volatile("wgmma.fence.sync.aligned;" ::: "memory"); }
__device__ __forceinline__ void wg_commit() { asm volatile("wgmma.commit_group.sync.aligned;" ::: "memory"); }
template <int N> __device__ __forceinline__ void wg_wait() { asm volatile("wgmma.wait_group.sync.aligned %0;" ::"n"(N) : "memory"); }
__device__ __forceinline__ uint64_t make_desc(uint32_t addr, uint32_t lbo, uint32_t sbo) {
  return (uint64_t)((addr & 0x3FFFF) >> 4) | ((uint64_t)(lbo >> 4) << 16) | ((uint64_t)(sbo >> 4) << 32) | (1ull << 62);
}
__device__ __forceinline__ uint32_t ld_relaxed(const uint32_t* p) {
  uint32_t v; asm volatile("ld.relaxed.gpu.global.u32 %0, [%1];" : "=r"(v) : "l"(p) : "memory"); return v;
}
__device__ __forceinline__ uint32_t ld_acquire(const uint32_t* p) {
  uint32_t v; asm volatile("ld.acquire.gpu.global.u32 %0, [%1];" : "=r"(v) : "l"(p) : "memory"); return v;
}
__device__ __forceinline__ uint4 ld_relaxed4(const uint32_t* p) {
  uint4 v; asm volatile("ld.relaxed.gpu.global.v4.u32 {%0,%1,%2,%3}, [%4];" : "=r"(v.x), "=r"(v.y), "=r"(v.z), "=r"(v.w) : "l"(p) : "memory"); return v;
}
__device__ __forceinline__ void st_relaxed(uint32_t* p, uint32_t v) {
  asm volatile("st.relaxed.gpu.global.u32 [%0], %1;" ::"l"(p), "r"(v) : "memory");
}
__device__ __forceinline__ void st_relaxed4(uint32_t* p, uint32_t a, uint32_t b, uint32_t c, uint32_t d) {
  asm volatile("st.relaxed.gpu.global.v4.u32 [%0], {%1,%2,%3,%4};" ::"l"(p), "r"(a), "r"(b), "r"(c), "r"(d) : "memory");
}
__device__ __forceinline__ void st_b128(uint32_t* p, uint32_t a, uint32_t b, uint32_t c, uint32_t d) {
  asm volatile("{ .reg .b64 u, v; .reg .b128 w; mov.b64 u, {%1, %2}; mov.b64 v, {%3, %4}; mov.b128 w, {u, v}; st.relaxed.gpu.global.b128 [%0], w; }"
               ::"l"(p), "r"(a), "r"(b), "r"(c), "r"(d) : "memory");
}
__device__ __forceinline__ uint4 ld_b128(const uint32_t* p) {
  uint4 r;
  asm volatile("{ .reg .b64 u, v; .reg .b128 w; ld.relaxed.gpu.global.b128 w, [%4]; mov.b128 {u, v}, w; mov.b64 {%0, %1}, u; mov.b64 {%2, %3}, v; }"
               : "=r"(r.x), "=r"(r.y), "=r"(r.z), "=r"(r.w) : "l"(p) : "memory");
  return r;
}
__device__ __forceinline__ void st_pairs(uint32_t* p, uint32_t a, uint32_t b, uint32_t tag) {
  asm volatile("{ .reg .b64 u, v; mov.b64 u, {%1, %3}; mov.b64 v, {%2, %3}; st.relaxed.gpu.global.v2.b64 [%0], {u, v}; }"
               ::"l"(p), "r"(a), "r"(b), "r"(tag) : "memory");
}
__device__ __forceinline__ uint4 ld_pairs(const uint32_t* p) {
  uint4 v;
  asm volatile("{ .reg .b64 u, v; ld.relaxed.gpu.global.v2.b64 {u, v}, [%4]; mov.b64 {%0, %1}, u; mov.b64 {%2, %3}, v; }"
               : "=r"(v.x), "=r"(v.y), "=r"(v.z), "=r"(v.w) : "l"(p) : "memory");
  return v;
}
__device__ __forceinline__ uint2 ld_pair(const uint32_t* p) {
  uint2 v;
  asm volatile("{ .reg .b64 u; ld.relaxed.gpu.global.b64 u, [%2]; mov.b64 {%0, %1}, u; }" : "=r"(v.x), "=r"(v.y) : "l"(p) : "memory");
  return v;
}
__device__ __forceinline__ void red_release(uint32_t* p, uint32_t v) {
  asm volatile("red.release.gpu.global.add.u32 [%0], %1;" ::"l"(p), "r"(v) : "memory");
}
__device__ __forceinline__ uint32_t ldg_nc1(const void* p) {
  uint32_t v;
  asm volatile("ld.global.nc.u32 %0, [%1];" : "=r"(v) : "l"(p));
  return v;
}
__device__ __forceinline__ uint4 ldg_nc4(const void* p) {
  uint4 v; asm volatile("ld.global.nc.L1::no_allocate.v4.u32 {%0,%1,%2,%3}, [%4];" : "=r"(v.x), "=r"(v.y), "=r"(v.z), "=r"(v.w) : "l"(p)); return v;
}
__device__ __forceinline__ uint4 ldg_stream4(const void* p) {
  uint4 v;
  asm volatile("ld.global.nc.L1::no_allocate.L2::cache_hint.v4.u32 {%0,%1,%2,%3}, [%4], %5;" : "=r"(v.x), "=r"(v.y), "=r"(v.z), "=r"(v.w) : "l"(p), "l"(l2_stream()));
  return v;
}
__device__ __forceinline__ void stg4(void* p, uint4 v) {
  asm volatile("st.global.v4.u32 [%0], {%1,%2,%3,%4};" ::"l"(p), "r"(v.x), "r"(v.y), "r"(v.z), "r"(v.w) : "memory");
}
__device__ __forceinline__ void wait_counter(const uint32_t* p, uint32_t target) {
  uint32_t n = 0;
  while (__any_sync(0xffffffffu, (int)(ld_acquire(p) - target) < 0)) { watchdog(n); }
}
__device__ __forceinline__ uint32_t tagf(float v, uint32_t tag) { return (__float_as_uint(v) & ~3u) | tag; }
__device__ __forceinline__ bool tag_ok(uint4 v, uint32_t tag) { return (((v.x ^ tag) | (v.y ^ tag) | (v.z ^ tag) | (v.w ^ tag)) & 3u) == 0; }
__device__ __forceinline__ float untag_sum(uint32_t a, uint32_t b) { return __uint_as_float(a & ~3u) + __uint_as_float(b & ~3u); }
__device__ __forceinline__ uint4 poll4(const uint32_t* p, uint32_t tag) {
  uint4 v = ld_relaxed4(p);
  uint32_t n = 0;
  while (!__all_sync(0xffffffffu, tag_ok(v, tag))) { v = ld_relaxed4(p); watchdog(n); }
  return v;
}
__device__ __forceinline__ float bf_lo(uint32_t v) { return __uint_as_float(v << 16); }
__device__ __forceinline__ float bf_hi(uint32_t v) { return __uint_as_float(v & 0xffff0000u); }
__device__ __forceinline__ uint32_t pack_bf(float lo, float hi) {
  uint32_t r; asm("cvt.rn.bf16x2.f32 %0, %1, %2;" : "=r"(r) : "f"(hi), "f"(lo)); return r;
}
__device__ __forceinline__ float rbf(float v) { return __uint_as_float(pack_bf(0.f, v) & 0xffff0000u); }
__device__ __forceinline__ uint32_t hmul2(uint32_t a, uint32_t b) {
  uint32_t r; asm("mul.rn.bf16x2 %0, %1, %2;" : "=r"(r) : "r"(a), "r"(b)); return r;
}
__device__ __forceinline__ uint32_t hadd2(uint32_t a, uint32_t b) {
  uint32_t r; asm("add.rn.bf16x2 %0, %1, %2;" : "=r"(r) : "r"(a), "r"(b)); return r;
}
__device__ __forceinline__ uint32_t hsub2(uint32_t a, uint32_t b) {
  uint32_t r; asm("sub.rn.bf16x2 %0, %1, %2;" : "=r"(r) : "r"(a), "r"(b)); return r;
}
__device__ __forceinline__ float rcp(float x) { float r; asm("rcp.approx.ftz.f32 %0, %1;" : "=f"(r) : "f"(x)); return r; }
__device__ __forceinline__ float ex2(float x) { float r; asm("ex2.approx.ftz.f32 %0, %1;" : "=f"(r) : "f"(x)); return r; }
__device__ __forceinline__ void stmatrix4(uint32_t addr, uint32_t a, uint32_t b, uint32_t c, uint32_t d) {
  asm volatile("stmatrix.sync.aligned.m8n8.x4.shared.b16 [%0], {%1,%2,%3,%4};" ::"r"(addr), "r"(a), "r"(b), "r"(c), "r"(d) : "memory");
}
__device__ __forceinline__ void ldmatrix4(uint32_t addr, uint32_t& a, uint32_t& b, uint32_t& c, uint32_t& d) {
  asm volatile("ldmatrix.sync.aligned.m8n8.x4.shared.b16 {%0,%1,%2,%3}, [%4];" : "=r"(a), "=r"(b), "=r"(c), "=r"(d) : "r"(addr) : "memory");
}
__device__ __forceinline__ void ldmatrix4t(uint32_t addr, uint32_t& a, uint32_t& b, uint32_t& c, uint32_t& d) {
  asm volatile("ldmatrix.sync.aligned.m8n8.x4.trans.shared.b16 {%0,%1,%2,%3}, [%4];" : "=r"(a), "=r"(b), "=r"(c), "=r"(d) : "r"(addr) : "memory");
}
__device__ __forceinline__ void mma16816(float (&d)[4], uint32_t a0, uint32_t a1, uint32_t a2, uint32_t a3, uint32_t b0, uint32_t b1) {
  asm volatile("mma.sync.aligned.m16n8k16.row.col.f32.bf16.bf16.f32 {%0,%1,%2,%3}, {%4,%5,%6,%7}, {%8,%9}, {%0,%1,%2,%3};"
               : "+f"(d[0]), "+f"(d[1]), "+f"(d[2]), "+f"(d[3]) : "r"(a0), "r"(a1), "r"(a2), "r"(a3), "r"(b0), "r"(b1));
}
__device__ __forceinline__ void sts1(uint32_t a, uint32_t v) { asm volatile("st.shared.u32 [%0], %1;" ::"r"(a), "r"(v) : "memory"); }
__device__ __forceinline__ uint4 lds4(uint32_t a) {
  uint4 v; asm volatile("ld.shared.v4.u32 {%0,%1,%2,%3}, [%4];" : "=r"(v.x), "=r"(v.y), "=r"(v.z), "=r"(v.w) : "r"(a) : "memory"); return v;
}
__device__ __forceinline__ uint2 lds2(uint32_t a) {
  uint2 v; asm volatile("ld.shared.v2.u32 {%0,%1}, [%2];" : "=r"(v.x), "=r"(v.y) : "r"(a) : "memory"); return v;
}
__device__ __forceinline__ uint32_t lds1(uint32_t a) {
  uint32_t v; asm volatile("ld.shared.u32 %0, [%1];" : "=r"(v) : "r"(a) : "memory"); return v;
}
__device__ __forceinline__ void sts2(uint32_t a, uint32_t x, uint32_t y) { asm volatile("st.shared.v2.u32 [%0], {%1,%2};" ::"r"(a), "r"(x), "r"(y) : "memory"); }
__device__ __forceinline__ void sts4(uint32_t a, uint4 v) {
  asm volatile("st.shared.v4.u32 [%0], {%1,%2,%3,%4};" ::"r"(a), "r"(v.x), "r"(v.y), "r"(v.z), "r"(v.w) : "memory");
}
__device__ __forceinline__ float silu_f(float v) { return __fdividef(v, 1.f + __expf(-v)); }
__device__ __forceinline__ uint32_t hfma2(uint32_t a, uint32_t b, uint32_t c) {
  uint32_t r; asm("fma.rn.bf16x2 %0, %1, %2, %3;" : "=r"(r) : "r"(a), "r"(b), "r"(c)); return r;
}
__device__ __forceinline__ void split_inv(float sd, uint32_t& ih, uint32_t& il) {
  const float inv = rcp(sd);
  ih = pack_bf(inv, inv);
  const float lo = inv - bf_lo(ih);
  il = pack_bf(lo, lo);
}
__device__ __forceinline__ uint32_t ln_norm(uint32_t x, uint32_t mean2, uint32_t ih, uint32_t il) {
  const uint32_t d = hsub2(x, mean2);
  return hfma2(d, ih, hmul2(d, il));
}
__device__ __forceinline__ uint32_t ln_mod(uint32_t x, uint32_t mean2, uint32_t ih, uint32_t il, uint32_t c1, uint32_t sh) {
  return hadd2(hmul2(ln_norm(x, mean2, ih, il), c1), sh);
}

#define R8(a, i) "+f"(a[i]), "+f"(a[i + 1]), "+f"(a[i + 2]), "+f"(a[i + 3]), "+f"(a[i + 4]), "+f"(a[i + 5]), "+f"(a[i + 6]), "+f"(a[i + 7])
#define D64 "{%0,%1,%2,%3,%4,%5,%6,%7,%8,%9,%10,%11,%12,%13,%14,%15,%16,%17,%18,%19,%20,%21,%22,%23,%24,%25,%26,%27,%28,%29,%30,%31," \
            "%32,%33,%34,%35,%36,%37,%38,%39,%40,%41,%42,%43,%44,%45,%46,%47,%48,%49,%50,%51,%52,%53,%54,%55,%56,%57,%58,%59,%60,%61,%62,%63}"
template <int TB>
__device__ __forceinline__ void mma_ss(float (&d)[64], uint64_t da, uint64_t db, int sc) {
  asm volatile("{\n.reg .pred p;\nsetp.ne.b32 p, %66, 0;\n"
               "wgmma.mma_async.sync.aligned.m64n128k16.f32.bf16.bf16 " D64 ", %64, %65, p, 1, 1, 0, %67;\n}"
               : R8(d, 0), R8(d, 8), R8(d, 16), R8(d, 24), R8(d, 32), R8(d, 40), R8(d, 48), R8(d, 56)
               : "l"(da), "l"(db), "r"(sc), "n"(TB));
}
template <int TB>
__device__ __forceinline__ void mma_rs(float (&d)[64], uint32_t a0, uint32_t a1, uint32_t a2, uint32_t a3, uint64_t db, int sc) {
  asm volatile("{\n.reg .pred p;\nsetp.ne.b32 p, %69, 0;\n"
               "wgmma.mma_async.sync.aligned.m64n128k16.f32.bf16.bf16 " D64 ", {%64,%65,%66,%67}, %68, p, 1, 1, %70;\n}"
               : R8(d, 0), R8(d, 8), R8(d, 16), R8(d, 24), R8(d, 32), R8(d, 40), R8(d, 48), R8(d, 56)
               : "r"(a0), "r"(a1), "r"(a2), "r"(a3), "l"(db), "r"(sc), "n"(TB));
}
#define D128 "{%0,%1,%2,%3,%4,%5,%6,%7,%8,%9,%10,%11,%12,%13,%14,%15,%16,%17,%18,%19,%20,%21,%22,%23,%24,%25,%26,%27,%28,%29,%30,%31," \
             "%32,%33,%34,%35,%36,%37,%38,%39,%40,%41,%42,%43,%44,%45,%46,%47,%48,%49,%50,%51,%52,%53,%54,%55,%56,%57,%58,%59,%60,%61,%62,%63," \
             "%64,%65,%66,%67,%68,%69,%70,%71,%72,%73,%74,%75,%76,%77,%78,%79,%80,%81,%82,%83,%84,%85,%86,%87,%88,%89,%90,%91,%92,%93,%94,%95," \
             "%96,%97,%98,%99,%100,%101,%102,%103,%104,%105,%106,%107,%108,%109,%110,%111,%112,%113,%114,%115,%116,%117,%118,%119,%120,%121,%122,%123,%124,%125,%126,%127}"
#define R128(d, e) R8(d, 0), R8(d, 8), R8(d, 16), R8(d, 24), R8(d, 32), R8(d, 40), R8(d, 48), R8(d, 56), \
                   R8(e, 0), R8(e, 8), R8(e, 16), R8(e, 24), R8(e, 32), R8(e, 40), R8(e, 48), R8(e, 56)
__device__ __forceinline__ void mma256_ss(float (&d)[64], float (&e)[64], uint64_t da, uint64_t db, int sc) {
  asm volatile("{\n.reg .pred p;\nsetp.ne.b32 p, %130, 0;\n"
               "wgmma.mma_async.sync.aligned.m64n256k16.f32.bf16.bf16 " D128 ", %128, %129, p, 1, 1, 0, 1;\n}"
               : R128(d, e) : "l"(da), "l"(db), "r"(sc));
}
__device__ __forceinline__ void mma256_rs(float (&d)[64], float (&e)[64], uint32_t a0, uint32_t a1, uint32_t a2, uint32_t a3, uint64_t db) {
  asm volatile("{\n.reg .pred p;\nsetp.ne.b32 p, 1, 0;\n"
               "wgmma.mma_async.sync.aligned.m64n256k16.f32.bf16.bf16 " D128 ", {%128,%129,%130,%131}, %132, p, 1, 1, 1;\n}"
               : R128(d, e) : "r"(a0), "r"(a1), "r"(a2), "r"(a3), "l"(db));
}
template <int N> __device__ __forceinline__ void keep(float (&a)[N]) {
#pragma unroll
  for (int i = 0; i < N; i++) asm volatile("" : "+f"(a[i])::"memory");
}
template <int N> __device__ __forceinline__ void keep(uint32_t (&a)[N]) {
#pragma unroll
  for (int i = 0; i < N; i++) asm volatile("" : "+r"(a[i])::"memory");
}

#define STAMP(idx) do {} while (0)
#define PROF(grp, cond, idx) do {} while (0)

constexpr float SCL2 = 1.4426950408889634f * 0.08838834764831845f;

__device__ __forceinline__ void pack_p(const float (&s)[64], uint32_t (&p)[32]) {
#pragma unroll
  for (int i = 0; i < 32; i++) p[i] = pack_bf(s[2 * i], s[2 * i + 1]);
}

__device__ __forceinline__ void issue_qk(float (&s)[64], uint32_t q0, uint32_t q1, uint32_t kslot) {
  const uint64_t db = make_desc(kslot, 16, 1024), da0 = make_desc(q0, 16, 1024), da1 = make_desc(q1, 16, 1024);
#pragma unroll
  for (int kk = 0; kk < 8; kk++) mma_ss<0>(s, (kk < 4 ? da0 : da1) + (kk & 3) * 2, db + (kk >> 2) * 1024 + (kk & 3) * 2, kk != 0);
}
__device__ __forceinline__ void issue_pv(float (&o)[64], uint32_t (&p)[32], uint32_t vslot, int acc) {
  uint64_t db = make_desc(vslot, 16384, 1024);
#pragma unroll
  for (int kk = 0; kk < 8; kk++)
    mma_rs<1>(o, p[4 * kk], p[4 * kk + 1], p[4 * kk + 2], p[4 * kk + 3], db + kk * 128, kk == 0 ? acc : 1);
}

template <int H>
__device__ __forceinline__ void store_chunk(const float (&a)[64], uint32_t addr) {
#pragma unroll
  for (int i = 8 * H; i < 8 * H + 8; i += 2)
    stmatrix4(addr ^ ((i & 7) << 4), pack_bf(a[4 * i], a[4 * i + 1]), pack_bf(a[4 * i + 2], a[4 * i + 3]),
              pack_bf(a[4 * i + 4], a[4 * i + 5]), pack_bf(a[4 * i + 6], a[4 * i + 7]));
}
template <int H>
__device__ __forceinline__ void store_chunk(const float (&a)[64], float i0, float i1, uint32_t addr) {
#pragma unroll
  for (int i = 8 * H; i < 8 * H + 8; i += 2)
    stmatrix4(addr ^ ((i & 7) << 4), pack_bf(a[4 * i] * i0, a[4 * i + 1] * i0), pack_bf(a[4 * i + 2] * i1, a[4 * i + 3] * i1),
              pack_bf(a[4 * i + 4] * i0, a[4 * i + 5] * i0), pack_bf(a[4 * i + 6] * i1, a[4 * i + 7] * i1));
}
__device__ __forceinline__ float inv_quad_sum(float l) {
  l += __shfl_xor_sync(0xffffffffu, l, 1);
  l += __shfl_xor_sync(0xffffffffu, l, 2);
  return rcp(l);
}

__device__ __forceinline__ void write_table(uint32_t table, bool ca, uint32_t t, const uint4& m0, const uint4& m1) {
  float c0 = untag_sum(m0.x, m1.x), c1 = untag_sum(m0.y, m1.y), c2 = untag_sum(m0.z, m1.z), c3 = untag_sum(m0.w, m1.w);
  if (ca) { c0 = 1.f + rbf(c0); c1 = 1.f + rbf(c1); c2 = 1.f + rbf(c2); c3 = 1.f + rbf(c3); }
  const uint32_t d = table + (t >> 2) * 64 + (t & 1) * 32 + (t & 2) * 2 + (ca ? 0 : 8);
  sts1(d, pack_bf(c0, c1));
  sts1(d + 16, pack_bf(c2, c3));
}

__device__ __forceinline__ void ln_scalars(float mean, float var, float& mb, float& sd) {
  mb = rbf(mean);
  float r; asm("sqrt.approx.ftz.f32 %0, %1;" : "=f"(r) : "f"(rbf(rbf(var) + 1e-5f)));
  sd = rbf(r);
}

__global__ void __cluster_dims__(2, 1, 1) __launch_bounds__(384, 1) fused_kernel(const __grid_constant__ Maps maps, const Ptrs P) {
  extern __shared__ __align__(1024) uint8_t smem_raw[];
  const uint32_t base = smem_u32(smem_raw);
  const int tid = threadIdx.x, lane = tid & 31;
  const int warp = __shfl_sync(0xffffffffu, tid >> 5, 0);
  int b = blockIdx.x;
  if (b < NMAIN) {
    const int p = b >> 1;
    const int grp = p < 4 ? 7 : (p < 36 ? (p + 2) & 7 : (p - 30) % 7), k = p < 4 ? 4 + p : (p < 36 ? (p - 4) >> 3 : 4 + (p - 36) / 7);
    b = grp << 4 | (KP ? (k & 3) * 2 + (k >> 2) : k) << 1 | (b & 1);
  }
  PROF(31, tid == 0, 0);

  if (b >= NMAIN) {
    float* sc = reinterpret_cast<float*>(smem_raw);
    float* red = sc + DM;
    for (int k = tid; k < DM; k += 384) sc[k] = rbf(silu_f(__bfloat162float(P.c[k])));
    __syncthreads();
    if (tid < 256) {
      const int col = 2048 + (b - NMAIN) * 1024 + (tid & 127) * 8, r0 = (tid >> 7) * 512;
      float acc[8];
#pragma unroll
      for (int e = 0; e < 8; e++) acc[e] = 0.f;
#pragma unroll 1
      for (int r = r0; r < r0 + 512; r += HU) {
        uint4 w[HU];
#pragma unroll
        for (int u = 0; u < HU; u++) w[u] = ldg_stream4(P.w_mod + (size_t)(r + u) * NMOD + col);
#pragma unroll
        for (int u = 0; u < HU; u++) {
          float s = sc[r + u];
          acc[0] += s * bf_lo(w[u].x); acc[1] += s * bf_hi(w[u].x); acc[2] += s * bf_lo(w[u].y); acc[3] += s * bf_hi(w[u].y);
          acc[4] += s * bf_lo(w[u].z); acc[5] += s * bf_hi(w[u].z); acc[6] += s * bf_lo(w[u].w); acc[7] += s * bf_hi(w[u].w);
        }
      }
      if (tid >= 128) {
#pragma unroll
        for (int e = 0; e < 8; e++) red[(tid & 127) * 8 + e] = acc[e];
      }
      const uint32_t tag = ld_relaxed(&g_epoch) % 3 + 1;
      bar_sync(1, 256);
      if (tid < 128) {
        uint32_t o[8];
#pragma unroll
        for (int e = 0; e < 8; e++) o[e] = __float_as_uint(rbf(acc[e] + red[tid * 8 + e])) | tag;
        st_relaxed4(g_mod + col, o[0], o[1], o[2], o[3]);
        st_relaxed4(g_mod + col + 4, o[4], o[5], o[6], o[7]);
        const uint4 wr = ldg_nc4(P.w_r + tid * 8);
        const uint32_t wv[4] = {wr.x, wr.y, wr.z, wr.w};
        float dsum = 0.f;
#pragma unroll
        for (int e = 0; e < 8; e++) {
          const float m = bf_hi(o[e]);
          dsum += (b == NMAIN + 2 ? rbf(1.f + m) : m) * ((e & 1) ? bf_hi(wv[e >> 1]) : bf_lo(wv[e >> 1]));
        }
#pragma unroll
        for (int k = 16; k > 0; k >>= 1) dsum += __shfl_xor_sync(0xffffffffu, dsum, k);
        if (lane == 0) st_relaxed(g_mod + (b - NMAIN) * 4 + warp, tagf(dsum, tag));
      }
    }
    PROF(2, tid == 0, 1);
    return;
  }

  const int rank = b & 1;
  const int rb = ((b >> 4) << 1) | rank, cj = (b >> 1) & 7;
  const bool late = b & 4;
  const uint32_t bfull = base + OFF_BAR, bempty = bfull + NSLOT * 8;
  const uint32_t gfull = bempty + NSLOT * 8, gempty = gfull + 32;
  const uint32_t bar_ofull = gempty + 32;
  const uint32_t bar_ofree = bar_ofull + 32;
  const uint32_t bar_par = bar_ofree + 32;
  const uint32_t bar_mod = bar_par + 8;
  const uint32_t bar_pread = bar_mod + 8;
  const uint32_t bar_xres = bar_pread + 8;
  const uint32_t bar_ring = bar_xres + 8;
  const uint32_t bar_box = bar_ring + 24;
  const uint32_t bar_go = bar_box + 96;
  const uint32_t bar_go2 = bar_go + 16;
  const uint32_t bar_cnt = bar_go + 24;
  const uint32_t xfull = bar_go + 40, xempty = xfull + 32;
  const uint32_t bar_hw = xempty + 32, bar_hx = bar_hw + 8;
  const uint32_t bar_hpub = bar_hx + 16;
  const uint32_t bar_win = bar_hpub + 16;
  const uint32_t bar_rx = bar_win + 8;
  const uint32_t bar_sel = bar_rx + 8;
  const uint32_t bar_gate = bar_sel + 8;
  const uint32_t bar_rel = bar_gate + 8;
  const uint32_t bar_od = bar_rel + 8;
  const uint32_t bar_mod2 = bar_od + 8;
  const uint32_t bar_res = bar_go + 8;
  const uint32_t stage = base + OFF_STAGE, par = base + OFF_PAR;

  if (warp == 10 && elect_one()) prefetch_map(&maps.wm);
  if (warp == 8 && elect_one()) {
    for (int s = 0; s < NSLOT; s++) { mbar_init(bfull + s * 8, 1); mbar_init(bempty + s * 8, 16); }
    for (int s = 0; s < 4; s++) { mbar_init(gfull + s * 8, 1); mbar_init(gempty + s * 8, 16); mbar_init(xfull + s * 8, 1); mbar_init(xempty + s * 8, 8); mbar_init(bar_ofree + s * 8, 1); mbar_init(bar_ofull + s * 8, 128); }
    mbar_init(bar_par, 64); mbar_init(bar_mod, 256); mbar_init(bar_pread, 2); mbar_init(bar_xres, 1);
    mbar_init(bar_ring, 8); mbar_init(bar_ring + 8, 8); mbar_init(bar_ring + 16, 8);
    mbar_init(bar_go, 1); mbar_init(bar_go2, 1); mbar_init(bar_cnt, 1); mbar_init(bar_cnt + 8, 1); mbar_init(bar_hpub, 8); mbar_init(bar_hpub + 8, 8); mbar_init(bar_res, 1); mbar_init(bar_win, 1); mbar_init(bar_rx, 1); mbar_init(bar_sel, 64); mbar_init(bar_gate, 8); mbar_init(bar_rel, 8); mbar_init(bar_od, 1); mbar_init(bar_mod2, 64);
    for (int s = 0; s < 12; s++) mbar_init(bar_box + s * 8, 1);
    asm volatile("fence.mbarrier_init.release.cluster;" ::: "memory");
    prefetch_map(&maps.x); prefetch_map(&maps.wq); prefetch_map(&maps.k); prefetch_map(&maps.v);
  }
  if (warp == 9 && elect_one()) {
    mbar_init(bar_hw, 1); mbar_init(bar_hx, 1); mbar_init(bar_hx + 8, 1);
    asm volatile("fence.mbarrier_init.release.cluster;" ::: "memory");
    mbar_expect_tx(bar_hw, 32768);
    mbar_expect_tx(bar_hx, 16384);
    mbar_expect_tx(bar_hx + 8, 16384);
    const __nv_bfloat16* xs = P.x + (size_t)(rb * 128 + cj * 16) * DM;
    bulk_load(base + 2 * GST_BYTES, xs, 16384, bar_hx);
    if (!late) {
      tma2d(stage, &maps.wm, (b >> 1) * 32, rank * 512, bar_hw);
      tma2d(stage + 16384, &maps.wm, (b >> 1) * 32, rank * 512 + 256, bar_hw);
    }
    bulk_load(base + 3 * GST_BYTES, xs + 8 * DM, 16384, bar_hx + 8);
  }
  cluster_arrive();

  if (warp >= 8) {
    asm volatile("setmaxnreg.dec.sync.aligned.u32 40;");
    if (warp < 10) bar_arrive(1, 320);
    const uint32_t epoch = ld_relaxed(&g_epoch);
    cluster_wait();
    if (warp == 8) {
      const int kvrow = (cj >> 1) * SK + (SK - WIN);
      int wch = cj * 8 + rank * 2;
#pragma unroll 1
      for (int ps = 0; ps < 3; ps++) {
        const CUtensorMap* mw = ps == 2 ? &maps.wo : &maps.wq;
        const uint32_t xt = ps == 1 ? XT1 : XT2, wt = ps == 0 ? WT0 : (ps == 1 ? WT1 : WT2);
        const int nst = ps == 2 ? 32 : 16;
#pragma unroll 1
        for (int i = 0; i < nst; i++) {
          const uint32_t bf = gfull + (i & 3) * 8;
          const int kt = ps == 2 ? otile_of(i, cj) : (ps ? i : slice_of(i) + (b & 14)) & 15;
          const uint32_t wd = base + unit_of(wt, i & 3) + rank * UNIT, xd = base + unit_of(xt, i & 3);
          const uint8_t* xs = g_act + (uint32_t)(rb * 80 + (ps - 1) * 16 + kt) * UNIT;
          if (ps == 0 && i == HD) mbar_wait(bar_mod, 0);
          const bool own = ps == 2 && i >= 2 && i < 6, pub = i == 0 || i == 20 || i == 26;
          if (ps == 2 && pub) mbar_wait(i ? bar_cnt + (i & 2) * 4 : bar_ofree + 24, 0);
          if (pub) fence_async();
          if (ps == 2 && i == 6) mbar_wait(bar_ofree + 16, 0);
          if (i == RES0) mbar_wait(bar_res, 0);
          mbar_wait(bf, ((i >> 2) & 1) ^ 1);
          if (elect_one()) {
            mbar_expect_tx(bf, ps && !own ? GST_BYTES : 2 * UNIT);
            if (ps && i < 2) bulk_load_stream(xd, xs, UNIT, bf);
            mbar_arrive_pred(bar_go, i == GOST);
            mbar_arrive_pred(bar_go2, ps == 1 && i == PG0);
            mbar_arrive_pred(bar_od, ps && i == (ps == 1 ? ODS1 : ODS) + 1);
            if (i == RES0) mbar_expect_tx(bar_xres, 32768);
          }
          const int wk = (i == 31 ? kt ^ (rank * 8) : kt) * 64, wc = i == 31 ? cj * 2 : wch;
          const uint64_t xp = i == 31 || (XN && i >= 20) ? l2_normal() : l2_stream();
          mbar_wait(ps && i < 4 ? bempty + i * 8 : gempty + (i & 3) * 8, ((i >> 2) & 1) ^ 1);
          if (elect_one()) {
            tma3d_mc<true>(wd, mw, 0, wk, wc, bf);
            if (ps && i > 2 && !own) bulk_load_stream(xd, xs, UNIT, bf, xp);
            if (i == RES0 || i == RES1) tma2d(base + OFF_RES + (i == RES1) * UNIT, &maps.x, cj * 128 + (i == RES1) * 64, rb * 128, bar_xres);
          }
          if (ps == 1 && i == 2) {
            mbar_wait(bar_ofree, 0);
            if (elect_one()) bulk_load_stream(xd, xs, UNIT, bf);
          }
        }
        if (ps == 2) break;
        wch = ps ? ((wch >> 3) ^ rank) * 2 : wch + 4;
#pragma unroll 1
        for (int u = 0; u < 16; u++) {
          const bool isk = (u == 0) || ((u & 1) && u < 15);
          const int blk = (isk ? (u + 1) >> 1 : (u == 15 ? 7 : (u >> 1) - 1)) & 3;
          const uint32_t sl = base + unit_of(ps ? AT1 : AT0, u & 3) + rank * UNIT, bf = bfull + (u & 3) * 8;
          mbar_wait(bf, ((u >> 2) & 1) ^ 1);
          if (elect_one()) mbar_expect_tx(bf, SLOT_BYTES);
          mbar_wait(u < 4 ? gempty + ((u + 1) >> 1) * 8 : bempty + (u & 3) * 8, ((u >> 2) & 1) ^ 1);
          if (elect_one()) {
            if (ps && u >= 7 && u != 8) tma3d_mc<true>(sl, isk ? &maps.k : &maps.v, 0, kvrow + blk * 128, rank, bf);
            else tma3d_mc<false>(sl, isk ? &maps.k : &maps.v, 0, kvrow + blk * 128, rank, bf);
          }
        }
      }
      if (elect_one()) mbar_expect_tx(bar_rx, UNIT);
      mbar_wait(bar_rel, 0);
      if (elect_one()) {
        bulk_load_stream(base + UNIT, g_act + (uint32_t)(rb * 80 + 16 + otile_of(31, cj ^ 1)) * UNIT, UNIT, bar_rx);
      }
      if (b < NFFN) {
#pragma unroll 1
        for (int u = 0; u < 12; u++) {
          const uint32_t dst = base + unit_of(u < 4 ? FT_G : (u < 8 ? FT_U : FT_D), u & 3);
          if (elect_one()) mbar_expect_tx(bar_box + u * 8, UNIT);
          if (u == 0 || u == 2 || u == 8) mbar_wait(bar_ring + (u == 8 ? 16 : u * 4), 0);
          const int fp = u < 8 ? FPACE0 : FPACE;
          if (u >= fp) mbar_wait(bar_box + (u - fp) * 8, 0);
          if (elect_one()) {
            if (u < 8) tma2d(dst, u < 4 ? &maps.wg : &maps.wu, b * 32, (u & 3) * 256, bar_box + u * 8);
            else tma3d(dst, &maps.wd, 0, b * 32, (u - 8) * 4, bar_box + u * 8);
          }
        }
      }
    } else if (warp == 9) {
      const uint32_t target = 8 * (epoch + 1);
      uint32_t hmask = 0;
#pragma unroll 1
      for (int i = 0; i < 16; i++) {
        if (i == HDX) mbar_wait(bar_mod, 0);
        const int kt = (2 * cj + slice_of(i)) & 15;
        const uint32_t need = i == 15 ? 0xffffu : 1u << kt;
        if (i >= NRS && (hmask & need) != need) {
          uint32_t n = 0;
          do { hmask = __ballot_sync(0xffffffffu, ld_acquire(&g_cnt_h[rb * 32 + (lane & 15)]) == epoch + 1); watchdog(n); } while ((hmask & need) != need);
          PROF(1, lane == 0 && i == NRS, 26);
          fence_async();
        }
        mbar_wait(xempty + (i & 3) * 8, ((i >> 2) & 1) ^ 1);
        if (elect_one()) {
          mbar_expect_tx(xfull + (i & 3) * 8, UNIT);
          if (i < NRS) tma2d(base + (i & 3) * GST_BYTES, &maps.x, kt * 64, rb * 128, xfull + (i & 3) * 8);
          else bulk_load_stream(base + (i & 3) * GST_BYTES, g_act + (uint32_t)(rb * 80 + kt) * UNIT, UNIT, xfull + (i & 3) * 8);
        }
      }
      prefetch_map(&maps.wo);
#pragma unroll 1
      for (int t = 0; t < 4; t++) {
        if (t & 1) mbar_wait(bar_od, t >> 1);
        const int ops = OPS >> (t & 1);
#pragma unroll 1
        for (int p = 0; p < 32768; p += ops) {
          const uint32_t w = p >> 14, c = (p >> 13) & 1, off = w * 8192 + (p & 8191);
          mbar_wait(bar_ofull + (t & 1) * 16 + w * 8, t >> 1);
          if (elect_one()) {
            bulk_store(g_act + (uint32_t)(rb * 80 + 16 + (cj * 4 + t) * 2 + c) * UNIT + off, base + unit_of(QT, 2 * t + c) + off, ops);
            asm volatile("cp.async.bulk.commit_group;" ::: "memory");
            asm volatile("cp.async.bulk.wait_group.read 0;" ::: "memory");
          }
        }
        if (elect_one()) {
          mbar_arrive(t < 3 ? bar_ofree + t * 8 : bar_res);
          asm volatile("cp.async.bulk.wait_group 0;" ::: "memory");
          fence_async();
          red_release(&g_cnt_o[((rb * 4 + t) * 2 + (cj & 1)) * 32], 2);
        }
        if (t) {
          wait_counter(&g_cnt_o[(rb * 8 + 2 * t + (cj & 1)) * 32], target);
          if (t & 1) wait_counter(&g_cnt_o[(rb * 8 + (t == 1 ? cj & 1 : 7 - (cj & 1))) * 32], target);
          if (elect_one()) mbar_arrive(t == 1 ? bar_ofree + 24 : bar_cnt + t * 8 - 16);
        }
      }
      PROF(2, lane == 0, 27);
      const uint32_t tag = epoch % 3 + 1;
      const uint32_t* inbox = g_cand + (b >> 4) % CR * 512 + (lane & 15) * CS;
      mbar_wait(bar_ring + 16, 0);
      uint32_t c0 = ld_relaxed(inbox), n = 0;
#define CAND_STEP(cv)                                                                                        \
      {                                                                                                      \
        const bool valid = (cv & 3u) == tag, all = __all_sync(0xffffffffu, valid);                           \
        const uint32_t best = __reduce_max_sync(0xffffffffu, valid ? cv : 0u);                               \
        const uint32_t blk = __ffs(__ballot_sync(0xffffffffu, cv == best)) - 1;                              \
        if (best) sts2(par + PAR_CONST + 56, best, (blk << 7 | (~best >> 2 & 127)) | (all ? 0x1800 : 0x800)); \
        if (all) break;                                                                                      \
        cv = ld_relaxed(inbox);                                                                              \
      }
      while (true) { CAND_STEP(c0) watchdog(n); }
    } else {
      const int t2 = tid - 320;
      if (late && warp == 10) {
        mbar_wait(bar_hx, 0);
        if (elect_one()) {
          tma2d(stage, &maps.wm, (b >> 1) * 32, rank * 512, bar_hw);
          tma2d(stage + 16384, &maps.wm, (b >> 1) * 32, rank * 512 + 256, bar_hw);
        }
      }
      {
        const uint32_t tag = epoch % 3 + 1;
        mbar_wait(bar_hx + 8, 0);
        mbar_wait(bar_hw, 0);
        __nanosleep(late ? OSL2 : OSL);
        {
          const uint32_t t7 = (warp & 1) * 64 + (lane >> 4) * 32 + 16 + (lane & 15);
          const uint32_t* pm = g_modp + ((cj * 128 + t7 * 4) & (DM - 1));
          uint4 m0, m1, m2, m3;
          uint32_t n = 0;
          do {
            m0 = ld_relaxed4(pm); m1 = ld_relaxed4(pm + 2 * DM); m2 = ld_relaxed4(pm + DM); m3 = ld_relaxed4(pm + 3 * DM);
            watchdog(n);
          } while (!__all_sync(0xffffffffu, tag_ok(m0, tag) && tag_ok(m1, tag) && tag_ok(m2, tag) && tag_ok(m3, tag)));
          write_table(par, false, t7, m0, m1);
          write_table(par, true, t7, m2, m3);
          mbar_arrive(bar_mod2);
        }
      }
      mbar_wait(bar_hpub + (warp & 1) * 8, 0);
      PROF(1, t2 == 0, 24);
#pragma unroll 1
      for (int c = 0; c < 8; c++) {
        const uint32_t off = (warp & 1) * UNIT + c * 2048 + lane * 16;
        uint8_t* dst = g_act + (uint32_t)(rb * 80 + cj * 2) * UNIT + off;
        const uint4 v0 = lds4(stage + off), v1 = lds4(stage + off + 512), v2 = lds4(stage + off + 1024), v3 = lds4(stage + off + 1536);
        stg4(dst, v0); stg4(dst + 512, v1); stg4(dst + 1024, v2); stg4(dst + 1536, v3);
      }
      __syncwarp();
      PROF(1, t2 == 0, 15);
      if (lane == 0) {
        mbar_arrive(bar_pread);
        red_release(&g_cnt_h[rb * 32 + cj * 2 + (warp & 1)], 1);
        PROF(1, t2 == 0, 25);
        prefetch_map(&maps.wg); prefetch_map(&maps.wu); prefetch_map(&maps.wd); prefetch_map(&maps.out);
      }
      __syncwarp();
      if (b < NFFN) {
        mbar_wait(bar_go2, 0);
        const __nv_bfloat16* pg = ((b & 1) ? P.w_up : P.w_gate) + (b >> 1) * 64 + (size_t)t2 * FF;
        const __nv_bfloat16* pd = P.w_down + (size_t)b * 32768 + t2 * 64;
        PROF(2, t2 == 0, 13);
#pragma unroll 1
        for (int i = 0; i < WN; i += WB) {
          uint32_t v[WB];
#pragma unroll
          for (int u = 0; u < WB; u++) {
            const int k = i + u;
            asm volatile("ld.global.cg.L2::128B.u32 %0, [%1];" : "=r"(v[u]) : "l"(k < 16 ? pg + (size_t)k * 64 * FF : pd + (k - 16) * 4096));
          }
#pragma unroll
          for (int u = 1; u < WB; u++) v[0] ^= v[u];
          sts1(par + PAR_SINK + t2 * 4, v[0]);
        }
        PROF(2, t2 == 0, 14);
      }
      const uint32_t tag = epoch % 3 + 1;
      mbar_wait(bar_go, 0);
      bar_sync(4, 64);
      if (warp == 10) {
        const uint32_t* src = g_mod + 2 * DM + cj * 128 + lane * 4;
        const uint2 wr = *reinterpret_cast<const uint2*>(P.w_r + cj * 128 + lane * 4);
        uint4 vga, vsb, vcb, vgb;
        uint32_t n = 0;
        do {
          vga = ld_relaxed4(src); vsb = ld_relaxed4(src + DM); vcb = ld_relaxed4(src + 2 * DM); vgb = ld_relaxed4(src + 3 * DM);
          watchdog(n);
        } while (!__all_sync(0xffffffffu, tag_ok(vga, tag) && tag_ok(vsb, tag) && tag_ok(vcb, tag) && tag_ok(vgb, tag)));
        const float c0 = rbf(1.f + bf_hi(vcb.x)), c1 = rbf(1.f + bf_hi(vcb.y)), c2 = rbf(1.f + bf_hi(vcb.z)), c3 = rbf(1.f + bf_hi(vcb.w));
        const float a0 = c0 * bf_lo(wr.x), a1 = c1 * bf_hi(wr.x), a2 = c2 * bf_lo(wr.y), a3 = c3 * bf_hi(wr.y);
        const uint32_t h0 = pack_bf(a0, a1), h1 = pack_bf(a2, a3);
        const uint32_t t1 = par + PAR_T1 + (lane >> 2) * 64 + (lane & 1) * 32 + (lane & 2) * 2;
        sts1(t1, h0); sts1(t1 + 8, pack_bf(a0 - bf_lo(h0), a1 - bf_hi(h0)));
        sts1(t1 + 16, h1); sts1(t1 + 24, pack_bf(a2 - bf_lo(h1), a3 - bf_hi(h1)));
        const uint32_t tg = par + PAR_SINK + (lane >> 3) * 64 + (lane & 1) * 32 + (lane & 6) * 2;
        sts1(tg, __byte_perm(vga.x, vga.y, 0x7632)); sts1(tg + 16, __byte_perm(vga.z, vga.w, 0x7632));
        sts4(par + PAR_T2 + lane * 32, make_uint4(pack_bf(c0, c1), __byte_perm(vsb.x, vsb.y, 0x7632), __byte_perm(vgb.x, vgb.y, 0x7632), __byte_perm(vga.x, vga.y, 0x7632)));
        sts4(par + PAR_T2 + lane * 32 + 16, make_uint4(pack_bf(c2, c3), __byte_perm(vsb.z, vsb.w, 0x7632), __byte_perm(vgb.z, vgb.w, 0x7632), __byte_perm(vga.z, vga.w, 0x7632)));
      } else {
        const uint4 g = poll4((lane & 8) ? g_mod + 8 - (lane & 1) * 4 : g_mod + 5 * DM + (b >> 4) * 128 + (lane & 7) * 16 + (b & 12), tag);
        sts1(par + PAR_CONST + 60, 0);
        if (lane < 8) sts1(par + PAR_CONST + 16 + lane * 4, (b & 2) ? ((b & 1) ? g.w : g.z) : ((b & 1) ? g.y : g.x));
        else if (lane < 10) sts2(par + PAR_CONST + (lane - 8) * 8, __float_as_uint(untag_sum(g.x, g.y) + untag_sum(g.z, g.w)), epoch);
      }
      __syncwarp();
#pragma unroll 1
      for (int q = 0; q < 32; q++) {
        st_b128(g_xch + ((size_t)b * 8 * 256 + q * 64 + t2) * 4, (epoch & 1) << 16, 0, 0, 0);
        __nanosleep(RSL);
      }
      for (int q = 0; q < 2; q++) st_relaxed4(g_stats + (((rb * 8 + q * 4 + (t2 >> 4)) * 8 + cj) * 16 + (t2 & 15)) * 4, 0, 0, 0, 0);
      if (b < NFFN)
        for (int q = 0; q < 2; q++) st_relaxed4(ypart_slot(b, q * 64 + t2), 0, 0, 0, 0);
      st_relaxed4(g_row + rb * 2 * DM + (t2 >> 5) * DM + cj * 128 + (t2 & 31) * 4, 0, 0, 0, 0);
      __threadfence();
      mbar_arrive(bar_par);
      mbar_wait(bar_gate, 0);
      uint32_t have = 0, n = 0;
      while (true) {
        const uint32_t st = lds1(par + PAR_CONST + 60) >> 7;
        if ((st & 31) != have) {
          const uint32_t* hsrc = g_row + (st & 15) * 2 * DM + t2 * 4;
          uint4 hv[4];
          bool ok = true;
#pragma unroll
          for (int i = 0; i < 4; i++) hv[i] = ld_pairs(hsrc + i * 256);
#pragma unroll
          for (int i = 0; i < 4; i++) {
            sts2(base + ((FT_G >> i * 4) & 15) * UNIT + (warp & 1) * 8192 + 256 + lane * 8, hv[i].x, hv[i].z);
            ok = ok && hv[i].y == tag && hv[i].w == tag;
          }
          have = __all_sync(0xffffffffu, ok) ? st & 31 : 0;
        }
        if ((st ^ have) == 32) break;
        watchdog(n);
      }
      mbar_arrive(bar_sel);
    }
    __syncwarp();
    cluster_arrive();
    {
      const uint32_t tag = epoch % 3 + 1, t3 = tid - 256;
      mbar_wait(bar_win, 0);
      uint2 win = lds2(par + PAR_CONST + 56);
      win.y &= 0x7ff;
      const uint32_t* fsrc = g_row + (win.y >> 7) * 2 * DM + (b >> 4) * 128 + (t3 & 7) * 16 + (b & 6) * 2 + ((b >> 2) & 2);
      const uint32_t* ysrc = ypart_slot(min(t3, NFFN - 1), b);
      uint2 fh = ld_pair(fsrc), fx = ld_pair(fsrc + DM);
      uint4 ya = ld_b128(ysrc);
      const float rwin = __uint_as_float(((int)win.x < 0 ? win.x & 0x7fffffffu : ~win.x) & ~0x1ffu);
      const float rs = rbf(rcp(1.f + __expf(-rbf(rwin))));
      uint32_t n = 0;
      while (__any_sync(0xffffffffu, fh.y != tag || fx.y != tag)) { fh = ld_pair(fsrc); fx = ld_pair(fsrc + DM); watchdog(n); }
      while (true) {
        const bool miss = ((ya.x & 1) | (ya.y & 1) << 1) != tag;
        if (!__any_sync(0xffffffffu, miss)) break;
        if (miss) ya = ld_b128(ysrc);
        watchdog(n);
      }
      PROF(8, t3 == 0, 5);
      float y[8] = {bf_lo(ya.x & ~1u), bf_hi(ya.x), bf_lo(ya.y & ~1u), bf_hi(ya.y), bf_lo(ya.z), bf_hi(ya.z), bf_lo(ya.w), bf_hi(ya.w)};
#pragma unroll
      for (int h = 4; h > 0; h >>= 1) {
        const bool up = lane & (h * 2);
#pragma unroll
        for (int e = 0; e < h; e++) y[e] = (up ? y[e + h] : y[e]) + __shfl_xor_sync(0xffffffffu, up ? y[e] : y[e + h], h * 2);
      }
      y[0] += __shfl_xor_sync(0xffffffffu, y[0], 1);
      if (!(lane & 1)) sts1(par + PAR_RED + 64 + t3 * 2, __float_as_uint(y[0]));
      bar_sync(4, 128);
      if (t3 < 8) {
        float y0 = 0.f;
#pragma unroll
        for (int w7 = 0; w7 < 7; w7++) y0 += __uint_as_float(lds1(par + PAR_RED + 64 + w7 * 32 + t3 * 4));
        const uint32_t gv = lds1(par + PAR_CONST + 16 + t3 * 4);
        const uint32_t upd = hmul2(pack_bf(y0, y0), pack_bf(rs, rs));
        const uint32_t r = hadd2(fx.x, hmul2(__byte_perm(gv, gv, 0x3232), hadd2(fh.x, upd)));
        reinterpret_cast<uint16_t*>(P.out)[(size_t)win.y * DM + (b >> 4) * 128 + t3 * 16 + (b & 15)] = (b & 1) ? r >> 16 : r;
        if (b == 0 && t3 == 0) st_relaxed(&g_epoch, epoch + 1);
      }
      PROF(31, t3 == 0, 36);
    }
    cluster_wait();
  } else {
    const int wg = warp >> 2;

    uint32_t tag;
    {
      uint32_t* const pmod = g_modp + rank * 2 * DM + (b >> 1) * 32 + lane;
      uint32_t* const pln = g_ln1 + (rb * 128 + cj * 16 + warp) * 4;
      uint32_t sc[8];
#pragma unroll
      for (int k = 0; k < 8; k++) sc[k] = ldg_nc1(P.c + rank * 512 + warp * 64 + k * 8 + (lane & 3) * 2);
      const uint32_t epoch = ld_relaxed(&g_epoch);
      if (warp == 0) st_relaxed(pmod, 0);
      if (lane == 0) { st_b128(pln, 0, 0, 0, 0); st_b128(pln + 32, 0, 0, 0, 0); }
      asm volatile("setmaxnreg.inc.sync.aligned.u32 232;");
      bar_sync(1, 320);
#pragma unroll
      for (int k = 0; k < 8; k++) sc[k] = pack_bf(silu_f(bf_lo(sc[k])), silu_f(bf_hi(sc[k])));
      keep(sc);
      tag = epoch % 3 + 1;
#pragma unroll
      for (int part = 0; part < 4; part++) {
        if (!(part & 1)) {
          const uint32_t xa = base + (2 + part / 2) * GST_BYTES + warp * 2048 + lane * 16;
          mbar_wait(bar_hx + part * 4, 0);
          float s0 = 0.f, s1 = 0.f, q0 = 0.f, q1 = 0.f;
#pragma unroll
          for (int q = 0; q < 4; q++) {
            const uint4 xv = lds4(xa + q * 512);
            const uint32_t u[4] = {xv.x, xv.y, xv.z, xv.w};
#pragma unroll
            for (int e = 0; e < 4; e++) { const float lo = bf_lo(u[e]), hi = bf_hi(u[e]); s0 += lo; s1 += hi; q0 += lo * lo; q1 += hi * hi; }
          }
          s0 += s1; q0 += q1;
#pragma unroll
          for (int o = 16; o > 0; o >>= 1) { s0 += __shfl_xor_sync(0xffffffffu, s0, o); q0 += __shfl_xor_sync(0xffffffffu, q0, o); }
          const float mean = s0 * (1.f / DM);
          float mb, sd;
          ln_scalars(mean, fmaxf(q0 * (1.f / DM) - mean * mean, 0.f), mb, sd);
          uint32_t ih, il;
          split_inv(sd, ih, il);
          if (lane == 0) st_b128(pln + part * 16, pack_bf(mb, mb), ih, il, tag);
          PROF(1, tid == 0 && part == 2, 4);
        } else if (late == (part == 3)) {
          const uint32_t fr = (lane & 7) + (lane >> 4) * 8, tq = lane & 3;
          const uint32_t wa = stage + warp * 4096 + fr * 64 + ((((lane >> 3) & 1) ^ ((fr >> 1) & 3)) << 4);
          float d0[4] = {0.f, 0.f, 0.f, 0.f}, d1[4] = {0.f, 0.f, 0.f, 0.f};
          mbar_wait(bar_hw, 0);
#pragma unroll
          for (int ks = 0; ks < 4; ks++) {
            uint32_t w[8];
            ldmatrix4t(wa + ks * 1024, w[0], w[1], w[2], w[3]);
            ldmatrix4t((wa ^ 32) + ks * 1024, w[4], w[5], w[6], w[7]);
            mma16816(d0, w[0], w[1], w[2], w[3], sc[2 * ks], sc[2 * ks + 1]);
            mma16816(d1, w[4], w[5], w[6], w[7], sc[2 * ks], sc[2 * ks + 1]);
          }
          sts1(base + 2 * GST_BYTES + warp * 2048 + (tq * 8 + (lane >> 2)) * 4, __float_as_uint((tq & 2) ? ((tq & 1) ? d1[2] : d1[0]) : ((tq & 1) ? d0[2] : d0[0])));
          bar_sync(1, 256);
          if (warp == 0) {
            float s = 0.f;
#pragma unroll
            for (int w8 = 0; w8 < 8; w8++) s += __uint_as_float(lds1(base + 2 * GST_BYTES + w8 * 2048 + lane * 4));
            st_relaxed(pmod, (__float_as_uint(s) & ~3u) | tag);
          }
          PROF(1, tid == 0, 3);
        }
      }
      cluster_wait();
      if (wg == 1) bar_arrive(2, 256);
    }

    float f0 = 0.f, f1 = 0.f;
    const uint32_t rempty = lane < 2 ? mapa(bempty, lane & 1) : 0;
    constexpr uint32_t GE = NSLOT * 8 + 32;
    float o[64], s[64];
#pragma unroll 1
    for (int ps = 0; ps < 3; ps++) {
      {
        const uint32_t xt = ps == 1 ? XT1 : XT2, wt = ps == 1 ? WT1 : WT2;
        const int nst = ps == 2 ? 28 : 14;
        if (ps == 0) {
          float ga[64], gb[64];
#pragma unroll
          for (int i = 0; i < 64; i++) { ga[i] = 0.f; gb[i] = 0.f; }
          uint32_t a[2][16];
          const uint32_t l = fresh_lane();
          uint32_t fa[4];
#pragma unroll
          for (int kk = 0; kk < 4; kk++) fa[kk] = (base + wg * 8192 + frag_offset(warp)) ^ (kk * 32);
          const uint32_t mt = par + (l & 3) * 16;
          auto fetch = [&](int i, uint32_t (&f)[16], uint32_t z) {
            mbar_wait(xfull + (i & 3) * 8, i >> 2);
#pragma unroll
            for (int kk = 0; kk < 4; kk++) ldmatrix4(fa[kk] + (i & 3) * GST_BYTES + z, f[4 * kk], f[4 * kk + 1], f[4 * kk + 2], f[4 * kk + 3]);
          };
          const bool oddw = warp & 2;
          uint4 r0, r1;
          {
            const uint32_t t7 = (warp & 1) * 64 + (l >> 4) * 32 + (l & 15);
            const uint32_t* pm = g_modp + wg * DM + ((cj * 128 + t7 * 4) & (DM - 1));
            const uint32_t* pr = g_ln1 + (rb * 128 + warp * 16 + (l >> 2)) * 4;
            uint4 m0 = make_uint4(tag, tag, tag, tag), m1 = m0;
            if (!oddw) { m0 = ld_relaxed4(pm); m1 = ld_relaxed4(pm + 2 * DM); }
            r0 = ld_b128(pr); r1 = ld_b128(pr + 32);
            fetch(0, a[0], 0); fetch(1, a[1], 0);
            uint32_t n = 0;
            bool written = false;
#pragma unroll 1
            while (true) {
              uint32_t miss;
              asm volatile("{ .reg .pred p0, p1, p2, p3; .reg .b32 t, u;\n"
                           "lop3.b32 t, %1, %2, %19, 0x7e; lop3.b32 u, %3, %4, %19, 0x7e; or.b32 t, t, u; and.b32 t, t, 3; setp.ne.u32 p0, t, 0;\n"
                           "lop3.b32 t, %5, %6, %19, 0x7e; lop3.b32 u, %7, %8, %19, 0x7e; or.b32 t, t, u; and.b32 t, t, 3; setp.ne.u32 p1, t, 0;\n"
                           "setp.ne.u32 p2, %12, %19; setp.ne.u32 p3, %16, %19;\n"
                           "@p0 ld.relaxed.gpu.global.v4.u32 {%1, %2, %3, %4}, [%17];\n"
                           "@p1 ld.relaxed.gpu.global.v4.u32 {%5, %6, %7, %8}, [%17 + 8192];\n"
                           "@p2 ld.relaxed.gpu.global.v4.u32 {%9, %10, %11, %12}, [%18];\n"
                           "@p3 ld.relaxed.gpu.global.v4.u32 {%13, %14, %15, %16}, [%18 + 128];\n"
                           "or.pred p0, p0, p1; or.pred p2, p2, p3; vote.sync.any.pred p0, p0, 0xffffffff; vote.sync.any.pred p2, p2, 0xffffffff;\n"
                           "selp.u32 t, 1, 0, p0; selp.u32 u, 2, 0, p2; or.b32 %0, t, u; }"
                           : "=r"(miss), "+r"(m0.x), "+r"(m0.y), "+r"(m0.z), "+r"(m0.w), "+r"(m1.x), "+r"(m1.y), "+r"(m1.z), "+r"(m1.w),
                             "+r"(r0.x), "+r"(r0.y), "+r"(r0.z), "+r"(r0.w), "+r"(r1.x), "+r"(r1.y), "+r"(r1.z), "+r"(r1.w)
                           : "l"(pm), "l"(pr), "r"(tag) : "memory");
              if (!(miss & 1) && !written) {
                written = true;
                if (!oddw) write_table(par, wg, t7, m0, m1);
                mbar_arrive(bar_mod);
              }
              if (!miss) break;
              watchdog(n);
            }
          }
          const uint32_t zero = r0.w ^ tag;
          auto normalize = [&](uint32_t (&f)[16]) {
#pragma unroll
            for (int k = 0; k < 16; k += 2) { f[k] = ln_norm(f[k], r0.x, r0.y, r0.z); f[k + 1] = ln_norm(f[k + 1], r1.x, r1.y, r1.z); }
          };
          auto modulate = [&](int i, uint32_t (&f)[16]) {
#pragma unroll
            for (int kk = 0; kk < 4; kk++) {
              const uint4 m = lds4(mt + slice_of(i) * 256 + kk * 64);
              f[4 * kk] = hfma2(f[4 * kk], m.x, m.z); f[4 * kk + 1] = hfma2(f[4 * kk + 1], m.x, m.z);
              f[4 * kk + 2] = hfma2(f[4 * kk + 2], m.y, m.w); f[4 * kk + 3] = hfma2(f[4 * kk + 3], m.y, m.w);
            }
            keep(f);
            mbar_arrive_pred(xempty + (i & 3) * 8, l == 0);
          };
          auto publish = [&](int u, uint32_t (&f)[16]) {
#pragma unroll
            for (int kk = 0; kk < 4; kk++) stmatrix4(fa[kk] + OFF_STAGE + u * UNIT, f[4 * kk], f[4 * kk + 1], f[4 * kk + 2], f[4 * kk + 3]);
            __syncwarp();
            mbar_arrive_pred(bar_hpub + u * 8, l == 0);
          };
          auto multiply = [&](int i, uint32_t (&f)[16]) {
            mbar_wait(gfull + (i & 3) * 8, i >> 2);
            const uint64_t db = make_desc(base + (i & 3) * GST_BYTES + UNIT, 8192, 1024);
            wg_fence();
#pragma unroll
            for (int kk = 0; kk < 4; kk++) mma256_rs(ga, gb, f[4 * kk], f[4 * kk + 1], f[4 * kk + 2], f[4 * kk + 3], db + kk * 128);
            wg_commit();
          };
          auto next = [&](int i, uint32_t (&f)[16]) {
            wg_wait<1>();
            mbar_arrive_cl(rempty, GE + ((i + 2) & 3) * 8);
            uint32_t z = zero;
#pragma unroll
            for (int k = 0; k < 16; k += 2) asm volatile("lop3.b32 %0, %1, %2, %0, 0xA8;" : "+r"(z) : "r"(f[k]), "r"(f[k + 1]));
            fetch(i, f, z);
            normalize(f);
            if (i == 2) { keep(f); mbar_wait(bar_mod2, 0); }
            modulate(i, f); multiply(i, f);
          };
          normalize(a[0]); normalize(a[1]);
          keep(a[0]); keep(a[1]);
          mbar_wait(bar_mod, 0);
          PROF(1, tid == 0, 2);
          modulate(0, a[0]); multiply(0, a[0]); publish(0, a[0]);
          modulate(1, a[1]); multiply(1, a[1]);
#pragma unroll 1
          for (int i = 2; i < NRS; i += 2) {
            next(i, a[0]);
            if (i == 2) publish(1, a[0]);
            next(i + 1, a[1]);
          }
          wg_wait<1>();
          mbar_arrive_cl(rempty, GE + ((NRS + 2) & 3) * 8);
#pragma unroll 1
          for (int i = NRS; i < 14; i++) {
            mbar_wait(xfull + (i & 3) * 8, (i >> 2) & 1);
            mbar_wait(gfull + (i & 3) * 8, (i >> 2) & 1);
            const uint32_t xa = base + (i & 3) * GST_BYTES;
            const uint64_t da = make_desc(xa + wg * 8192, 16, 1024), db = make_desc(xa + UNIT, 8192, 1024);
            if (i == 13) bar_sync(2 + wg, 256);
            wg_fence();
#pragma unroll
            for (int kk = 0; kk < 4; kk++) mma256_ss(ga, gb, da + kk * 2, db + kk * 128, 1);
            wg_commit();
            if (i == 13) bar_arrive(3 - wg, 256);
            wg_wait<1>();
            uint32_t z = zero;
#pragma unroll
            for (int k = 0; k < 16; k += 2) asm volatile("lop3.b32 %0, %1, %2, %0, 0xA8;" : "+r"(z) : "r"(a[1][k]), "r"(a[1][k + 1]));
            mbar_arrive_cl(rempty, GE + ((i + 3) & 3) * 8 + z);
            mbar_arrive_pred(xempty + ((i + 3) & 3) * 8, l == 0 && i != NRS);
          }
          mbar_wait(xfull + 16, 1);
          wg_wait<0>();
          keep(ga); keep(gb);
#pragma unroll
          for (int i = 0; i < 64; i++) {
            asm volatile("mov.b32 %0, %1;" : "=f"(s[i]) : "f"(ga[i]));
            asm volatile("mov.b32 %0, %1;" : "=f"(o[i]) : "f"(gb[i]));
          }
        } else {
          float ga[64], gb[64];
#pragma unroll
          for (int i = 0; i < 64; i++) {
            asm volatile("mov.b32 %0, %1;" : "=f"(ga[i]) : "f"(s[i]));
            asm volatile("mov.b32 %0, %1;" : "=f"(gb[i]) : "f"(o[i]));
          }
#pragma unroll 1
          for (int i = 0; i < nst; i++) {
            mbar_wait(gfull + (i & 3) * 8, (i >> 2) & 1);
            const uint64_t da = make_desc(base + unit_of(ps == 2 && (i >> 2) == 1 ? XT2B : xt, i & 3) + wg * 8192, 16, 1024), db = make_desc(base + unit_of(wt, i & 3), 8192, 1024);
            if (i == nst - 1) bar_sync(2 + wg, 256);
            wg_fence();
#pragma unroll
            for (int kk = 0; kk < 4; kk++) mma256_ss(ga, gb, da + kk * 2, db + kk * 128, kk ? 1 : i);
            wg_commit();
            if (i == nst - 1) bar_arrive(3 - wg, 256);
            wg_wait<1>();
            mbar_arrive_cl(rempty, GE + ((i + 3) & 3) * 8, i != 0);
            PROF(4, tid == 0 && (i & 3) == 0, 40 + (ps - 1) * 4 + i / 4);
          }
          wg_wait<0>();
          keep(ga); keep(gb);
#pragma unroll
          for (int i = 0; i < 64; i++) {
            asm volatile("mov.b32 %0, %1;" : "=f"(s[i]) : "f"(ga[i]));
            asm volatile("mov.b32 %0, %1;" : "=f"(o[i]) : "f"(gb[i]));
          }
        }
        mbar_arrive_cl(rempty, GE + (ps == 2 ? 24 : 8));
        if (ps == 2) break;
      }
      const uint32_t qw = base + wg * 8192, qt = QT >> (16 * ps), at = ps ? AT1 : AT0;
      {
        const uint32_t wt = ps ? WT1 : WT0;
        const uint64_t da0 = make_desc(qw + unit_of(qt, 2), 16, 1024), da1 = make_desc(qw + unit_of(qt, 3), 16, 1024);
        const uint64_t db0 = make_desc(base + unit_of(wt, 2), 8192, 1024), db1 = make_desc(base + unit_of(wt, 3), 8192, 1024);
        mbar_wait(gfull + 16, 1);
        bar_sync(2 + wg, 256);
        wg_fence();
#pragma unroll
        for (int kk = 0; kk < 4; kk++) mma_ss<1>(s, da0 + kk * 2, db0 + kk * 128, 1);
        wg_commit();
        mbar_wait(xfull + 24, 1);
        mbar_wait(gfull + 24, 1);
        wg_fence();
#pragma unroll
        for (int kk = 0; kk < 4; kk++) mma_ss<1>(s, da1 + kk * 2, db1 + kk * 128, 1);
        wg_commit();
        bar_arrive(3 - wg, 256);
        mbar_wait(ps == 0 ? bar_pread : bar_ofree + 8, 0);
        wg_wait<0>();
        keep(s);
        PROF(2, tid == 0, 8 + ps * 8);
        uint32_t q[32];
        pack_p(s, q);
#pragma unroll
        for (int i = 0; i < 4; i++) stmatrix4((qw + unit_of(qt, 0) + frag_offset(warp)) ^ (i << 5), q[4 * i], q[4 * i + 1], q[4 * i + 2], q[4 * i + 3]);
        keep(q);
        bar_sync(2 + wg, 256);
        wg_fence();
#pragma unroll
        for (int kk = 0; kk < 8; kk++) mma_ss<1>(o, (kk < 4 ? da0 : da1) + (kk & 3) * 2, (kk < 4 ? db0 : db1) + UNIT / 16 + (kk & 3) * 128, 1);
        wg_commit();
        mbar_wait(bfull, 0);
        wg_fence();
        const uint64_t dk = make_desc(base + unit_of(at, 0), 16, 1024);
#pragma unroll
        for (int kk = 0; kk < 8; kk++) mma_rs<0>(s, q[4 * kk], q[4 * kk + 1], q[4 * kk + 2], q[4 * kk + 3], dk + (kk >> 2) * 1024 + (kk & 3) * 2, kk != 0);
        wg_commit();
        bar_arrive(3 - wg, 256);
#pragma unroll
        for (int i = 4; i < 8; i++) stmatrix4((qw + unit_of(qt, 1) + frag_offset(warp)) ^ ((i & 3) << 5), q[4 * i], q[4 * i + 1], q[4 * i + 2], q[4 * i + 3]);
        wg_wait<1>();
        keep(o);
        mbar_arrive_cl(rempty, GE + 16);
        mbar_arrive_cl(rempty, GE + 24);
        store_chunk<0>(o, qw + unit_of(qt, 2) + frag_offset(warp));
        store_chunk<1>(o, qw + unit_of(qt, 3) + frag_offset(warp));
        wg_wait<0>();
        keep(s);
        mbar_arrive_cl(rempty, 0);
      }
      PROF(4, tid == 0 && ps == 1, 61);
      float l0 = 0.f, l1 = 0.f;
      auto step = [&](auto odd_c, const int j, uint32_t (&pw)[32], uint32_t (&pr)[32]) {
        constexpr bool ODD = decltype(odd_c)::value;
        const bool first = !ODD && (j & 2) == 0, last = ODD && j == 7;
        const uint32_t ph = (j >> 1) & 1;
        float i0, i1, a0, a1;
        const bool so = !ODD && j == 4;
        if (so) { i0 = inv_quad_sum(l0); i1 = inv_quad_sum(l1); l0 = 0.f; l1 = 0.f; }
        bool redo = !ODD && (j | ps) == 0;
        while (true) {
          if (redo) {
            float m0 = fmaxf(s[0], s[1]), m1 = fmaxf(s[2], s[3]);
#pragma unroll
            for (int i = 1; i < 16; i++) { m0 = fmaxf(m0, fmaxf(s[4 * i], s[4 * i + 1])); m1 = fmaxf(m1, fmaxf(s[4 * i + 2], s[4 * i + 3])); }
            m0 = fmaxf(m0, __shfl_xor_sync(0xffffffffu, m0, 1)); m1 = fmaxf(m1, __shfl_xor_sync(0xffffffffu, m1, 1));
            m0 = fmaxf(m0, __shfl_xor_sync(0xffffffffu, m0, 2)); m1 = fmaxf(m1, __shfl_xor_sync(0xffffffffu, m1, 2));
            m0 *= SCL2; m1 *= SCL2;
            if (!first) {
              m0 = fmaxf(m0, f0); m1 = fmaxf(m1, f1);
              const float c0 = ex2(f0 - m0), c1 = ex2(f1 - m1);
              l0 *= c0; l1 *= c1;
              wg_wait<0>();
              keep(o);
#pragma unroll
              for (int i = 0; i < 16; i++) { o[4 * i] *= c0; o[4 * i + 1] *= c0; o[4 * i + 2] *= c1; o[4 * i + 3] *= c1; }
            }
            f0 = m0; f1 = m1;
          }
          float b0 = 0.f, b1 = 0.f;
          a0 = 0.f; a1 = 0.f;
#pragma unroll
          for (int i = 0; i < 16; i++) {
            const float e0 = ex2(fmaf(s[4 * i], SCL2, -f0)), e1 = ex2(fmaf(s[4 * i + 1], SCL2, -f0));
            const float e2 = ex2(fmaf(s[4 * i + 2], SCL2, -f1)), e3 = ex2(fmaf(s[4 * i + 3], SCL2, -f1));
            a0 += e0; b0 += e1; a1 += e2; b1 += e3;
            pw[2 * i] = pack_bf(e0, e1); pw[2 * i + 1] = pack_bf(e2, e3);
            if (i == VREL) {
#pragma unroll
              for (int k = 0; k < 2 * VREL + 2; k++) asm volatile("" : "+r"(pw[k])::"memory");
              mbar_wait(bar_mod, 0);
              wg_wait<0>();
              mbar_arrive_cl(rempty, ODD ? 16 : 0, !redo && (ODD || j));
#pragma unroll
              for (int k = 4 * VREL + 4; k < 64; k++) asm volatile("" : "+f"(s[k])::"memory");
            }
          }
          a0 += b0; a1 += b1;
          if (redo) break;
          redo = __any_sync(0xffffffffu, !(a0 + a1 < 0x1p90f) || (!ODD && fminf(a0, a1) < (first ? 0x1p-90f : 0.f)));
          if (!redo) break;
        }
        l0 += a0; l1 += a1;
        keep(pw);
        keep(o);
        if (so) store_chunk<0>(o, i0, i1, qw + unit_of(qt, 0) + frag_offset(warp));
        keep(o);
        if (j == (ODD ? 5 : 0)) { fence_async_smem(); if (ODD) mbar_arrive(bar_ofull + wg * 8); }
        mbar_wait(bfull + (ODD ? 24 : 8), ph);
        bar_sync(2 + wg, 256);
        if (!last) {
          const uint32_t qn = qt >> (j >= 3 ? 8 : 0);
          wg_fence();
          issue_qk(s, qw + unit_of(qn, 0), qw + unit_of(qn, 1), base + unit_of(at, ODD ? 3 : 1));
          wg_commit();
          mbar_wait(bfull + (ODD ? 0 : 16), ODD ? ph ^ 1 : ph);
        }
        if (so) { store_chunk<1>(o, i0, i1, qw + unit_of(qt, 1) + frag_offset(warp)); keep(o); }
        wg_fence();
        issue_pv(o, pw, base + unit_of(at, ODD ? (last ? 3 : 0) : 2), !first);
        wg_commit();
        bar_arrive(3 - wg, 256);
        wg_wait<1>();
        keep(s);
        mbar_arrive_cl(rempty, ODD ? 24 : 8, !last);
        PROF(4, tid == 0 && ps == 1, 51 + j);
      };
      uint32_t pa[32], pb[32];
#pragma unroll 1
      for (int j = 0; j < 8; j += 2) {
        step(std::false_type{}, j, pa, pb);
        step(std::true_type{}, j + 1, pb, pa);
      }
      {
        const float i0 = inv_quad_sum(l0), i1 = inv_quad_sum(l1);
        wg_wait<0>();
        keep(o);
        mbar_arrive_cl(rempty, 24);
        store_chunk<0>(o, i0, i1, qw + unit_of(qt, 2) + frag_offset(warp));
        store_chunk<1>(o, i0, i1, qw + unit_of(qt, 3) + frag_offset(warp));
        fence_async_smem();
        mbar_arrive(bar_ofull + 16 + wg * 8);
      }
      PROF(2, tid == 0, 10 + ps * 8);
    }

    const int ln = fresh_lane(), g = ln >> 2, tq = ln & 3, ct = warp * 32 + ln;
    const bool lane0 = ln == 0;
    const int lrow0 = warp * 16 + g;
    const uint32_t res = base + OFF_RES, trow = res + wg * 8192 + frag_offset(warp);
    uint32_t xr[32];
    uint4 sv[4], own;
    uint32_t* const sg = g_stats + (rb * 8 + warp) * 512 + g * 4;
    uint32_t* sp[4];
#pragma unroll
    for (int k = 0; k < 4; k++) sp[k] = sg + (tq & 1) * 32 + (((tq >> 1) ^ (cj >> 2)) * 4 + (k ^ (cj & 3))) * 64;
    {
      const uint64_t da = make_desc(base + wg * 8192, 16, 1024), db = make_desc(base, 8192, 1024);
      constexpr int U = UNIT / 16;
#define HALF_STAGE(acc, xu, wu) _Pragma("unroll") for (int kk = 0; kk < 4; kk++) mma_ss<1>(acc, da + (xu) * U + kk * 2, db + (wu) * U + kk * 128, 1)
      PROF(10, ct == PT, 19); STAMP(0);
      cluster_arrive();
      mbar_wait(gfull, 1);
      mbar_wait(gfull + 8, 1);
      bar_sync(2 + wg, 256);
      wg_fence();
      HALF_STAGE(o, 7, 1);
      HALF_STAGE(o, 8, 3);
      wg_commit();
      STAMP(16);
      mbar_wait(gfull + 16, 1);
      STAMP(17);
      wg_fence();
      HALF_STAGE(o, 6, 11);
      wg_commit();
      bar_arrive(3 - wg, 256);
      mbar_wait(bar_par, 0);
      uint32_t* xo = g_xch + ((size_t)b * 8 * 256 + ct) * 4;
      const uint32_t* xi = g_xch + ((size_t)(b ^ 2) * 8 * 256 + ct) * 4;
      const uint32_t par1 = (~lds1(par + PAR_CONST + 4) & 1) << 16;
      wg_wait<1>();
      mbar_arrive_pred(bar_rel, lane0);
      wg_wait<0>();
      keep(o);
      mbar_arrive_pred(bar_ring, lane0);
      PROF(8, ct == PT, 20); STAMP(1);
#define SEND(i) st_b128(xo + (i) * 1024, (pack_bf(o[8 * (i)], o[8 * (i) + 1]) & ~0x10000u) | par1, pack_bf(o[8 * (i) + 2], o[8 * (i) + 3]), \
                        pack_bf(o[8 * (i) + 4], o[8 * (i) + 5]), pack_bf(o[8 * (i) + 6], o[8 * (i) + 7]))
#pragma unroll
      for (int i = 0; i < NS1; i++) SEND(i);
      PROF(8, ct == PT, 21); STAMP(2);
      bar_sync(2 + wg, 256);
      wg_fence();
      HALF_STAGE(s, 7, 0);
      HALF_STAGE(s, 8, 2);
      HALF_STAGE(s, 6, 10);
      wg_commit();
      bar_arrive(3 - wg, 256);
      STAMP(18);
      mbar_wait(gfull + 24, 1);
#pragma unroll
      for (int i = NS1; i < 8; i++) SEND(i);
      uint4 v[8];
      STAMP(19);
      mbar_wait(bar_xres, 0);
      wg_wait<0>();
      mbar_arrive_pred(bar_ring + 8, lane0);
      bar_sync(2 + wg, 256);
      STAMP(20);
#pragma unroll
      for (int i = 0; i < LD2; i++) v[i] = ld_b128(xi + i * 1024);
      mbar_wait(bar_xres, 0);
      wg_fence();
      HALF_STAGE(s, 9, 4);
      wg_commit();
      mbar_wait(bar_rx, 0);
      wg_fence();
      HALF_STAGE(s, 1, 5);
      wg_commit();
      bar_arrive(3 - wg, 256);
      STAMP(21);
#pragma unroll
      for (int i = LD2; i < 8; i++) v[i] = ld_b128(xi + i * 1024);
      mbar_wait(bar_xres, 0);
      wg_wait<0>();
      keep(s);
      mbar_arrive_pred(bar_ring + 16, lane0);
      PROF(10, ct == PT, 23); STAMP(4);
#pragma unroll
      for (int i = 0; i < 16; i += 2) ldmatrix4((trow ^ ((i & 7) << 4)) + (i >> 3) * 16384, xr[2 * i], xr[2 * i + 1], xr[2 * i + 2], xr[2 * i + 3]);
      uint32_t ga[16];
      uint4 bw[8];
#pragma unroll
      for (int i = 0; i < 8; i++) {
        if (!(i & 1)) {
          const uint4 t = lds4(par + PAR_SINK + i * 32 + tq * 16);
          ga[2 * i] = t.x; ga[2 * i + 1] = t.y; ga[2 * i + 2] = t.z; ga[2 * i + 3] = t.w;
        }
        bw[i] = lds4(par + PAR_T1 + i * 64 + tq * 16);
        if (!(g & 1)) { bw[i].x = 0x3f803f80u; bw[i].y = 0x3f803f80u; }
      }
      uint32_t pk[32];
      pack_p(s, pk);
      const uint32_t par2 = (~lds1(par + PAR_CONST + 12) & 1) << 16;
      {
        uint32_t n = 0, miss;
        do {
          miss = 0;
#pragma unroll
          for (int i = 0; i < 8; i++) miss |= v[i].x ^ par2;
          miss = __any_sync(0xffffffffu, miss & 0x10000u);
          if (miss) {
#pragma unroll
            for (int i = 0; i < 8; i++)
              asm volatile("{ .reg .pred p; .reg .b32 t; xor.b32 t, %0, %5; and.b32 t, t, 0x10000; setp.ne.u32 p, t, 0;\n"
                           "@p ld.relaxed.gpu.global.v4.u32 {%0, %1, %2, %3}, [%4]; }"
                           : "+r"(v[i].x), "+r"(v[i].y), "+r"(v[i].z), "+r"(v[i].w) : "l"(xi + i * 1024), "r"(par1) : "memory");
          }
          watchdog(n);
        } while (miss);
      }
      PROF(8, ct == PT, 22); STAMP(3);
      float ds[4] = {0.f, 0.f, 0.f, 0.f}, dl[4] = {0.f, 0.f, 0.f, 0.f}, q0[4] = {0.f, 0.f, 0.f, 0.f}, q1[4] = {0.f, 0.f, 0.f, 0.f};
#pragma unroll
      for (int i = 0; i < 8; i++) {
        const uint32_t u0 = hfma2(ga[2 * i], hadd2(pk[4 * i], v[i].x & ~0x10000u), xr[4 * i]);
        const uint32_t u1 = hfma2(ga[2 * i], hadd2(pk[4 * i + 1], v[i].y), xr[4 * i + 1]);
        const uint32_t u2 = hfma2(ga[2 * i + 1], hadd2(pk[4 * i + 2], v[i].z), xr[4 * i + 2]);
        const uint32_t u3 = hfma2(ga[2 * i + 1], hadd2(pk[4 * i + 3], v[i].w), xr[4 * i + 3]);
        xr[4 * i] = u0; xr[4 * i + 1] = u1; xr[4 * i + 2] = u2; xr[4 * i + 3] = u3;
        mma16816(ds, u0, u1, u2, u3, bw[i].x, bw[i].y);
        mma16816(dl, u0, u1, u2, u3, bw[i].z, bw[i].w);
        mma16816(q0, u0, u1, u2, u3, u0, u2);
        mma16816(q1, u0, u1, u2, u3, u1, u3);
      }
      const float sqa = (g & 1) ? q0[1] : q0[0], sqb = (g & 1) ? q1[3] : q1[2], dta = ds[1] + dl[1], dtb = ds[3] + dl[3];
      if (tq == (g >> 1)) {
        st_b128(sg + cj * 64, __float_as_uint(ds[0]), __float_as_uint(sqa), __float_as_uint(dta), tag);
        st_b128(sg + cj * 64 + 32, __float_as_uint(ds[2]), __float_as_uint(sqb), __float_as_uint(dtb), tag);
      }
#pragma unroll
      for (int k = 0; k < 4; k++) sv[k] = ld_b128(sp[k]);
      mbar_wait(bar_xres, 0);
      const float sqc = __shfl_sync(0xffffffffu, sqa, g * 4 + (g >> 1)), sqd = __shfl_sync(0xffffffffu, sqb, g * 4 + (g >> 1));
      own = (tq & 1) ? make_uint4(__float_as_uint(ds[2]), __float_as_uint(sqd), __float_as_uint(dtb), tag)
                     : make_uint4(__float_as_uint(ds[0]), __float_as_uint(sqc), __float_as_uint(dta), tag);
    }
    PROF(8, ct == PT, 29); STAMP(5);
    uint32_t mm, ih, il;
    float rbest;
    uint32_t wf[128];
    const uint32_t frow = (ln & 7) + (ln >> 4) * 8;
    const uint32_t wfo = base + (warp & 1) * 8192 + frow * 64 + ((((ln >> 3) & 1) ^ ((frow >> 1) & 3)) << 4);
#define LOAD_WF(m) _Pragma("unroll") for (int f = 0; f < 16; f++) {                                                   \
      const int r = ((f >> 1) * 4 + (m) * 2 + (f & 1)) * 4;                                                           \
      ldmatrix4t(((wfo + unit_of((m) ? FT_U : FT_G, warp >> 1)) ^ ((f & 1) * 32)) + (f >> 1) * 1024, wf[r], wf[r + 1], wf[r + 2], wf[r + 3]); \
    }
    bool early;
    {
#pragma unroll
      for (int i = 0; i < 16; i += 2) stmatrix4((trow ^ ((i & 7) << 4)) + (i >> 3) * 16384, xr[2 * i], xr[2 * i + 1], xr[2 * i + 2], xr[2 * i + 3]);
      const uint4 cst = lds4(par + PAR_CONST);
      const float A1 = __uint_as_float(cst.x), A2 = __uint_as_float(cst.z);
      uint32_t n = 0;
      early = false;
#pragma unroll 1
      while (true) {
        if (!early && (b >= NFFN || __all_sync(0xffffffffu, mbar_test(bar_box + (warp >> 1) * 8, 0)))) {
          early = true;
          LOAD_WF(0);
          __syncwarp();
          mbar_arrive_pred(bar_gate, lane0);
        }
        uint32_t miss;
        asm volatile("{ .reg .pred p0, p1, p2, p3; .reg .b64 u, v; .reg .b128 w;\n"
                     "setp.ge.u32 p0, %22, 2; setp.ne.and.u32 p0, %4, %21, p0; setp.ne.u32 p1, %8, %21; setp.ne.u32 p2, %12, %21; setp.ne.u32 p3, %16, %21;\n"
                     "@p0 ld.relaxed.gpu.global.v4.u32 {%1, %2, %3, %4}, [%17];\n"
                     "@p1 ld.relaxed.gpu.global.v4.u32 {%5, %6, %7, %8}, [%18];\n"
                     "@p2 ld.relaxed.gpu.global.v4.u32 {%9, %10, %11, %12}, [%19];\n"
                     "@p3 ld.relaxed.gpu.global.v4.u32 {%13, %14, %15, %16}, [%20];\n"
                     "or.pred p0, p0, p1; or.pred p2, p2, p3; or.pred p0, p0, p2; vote.sync.any.pred p0, p0, 0xffffffff; selp.u32 %0, 1, 0, p0; }"
                     : "=r"(miss), "+r"(sv[0].x), "+r"(sv[0].y), "+r"(sv[0].z), "+r"(sv[0].w), "+r"(sv[1].x), "+r"(sv[1].y), "+r"(sv[1].z), "+r"(sv[1].w),
                       "+r"(sv[2].x), "+r"(sv[2].y), "+r"(sv[2].z), "+r"(sv[2].w), "+r"(sv[3].x), "+r"(sv[3].y), "+r"(sv[3].z), "+r"(sv[3].w)
                     : "l"(sp[0]), "l"(sp[1]), "l"(sp[2]), "l"(sp[3]), "r"(tag), "r"(tq) : "memory");
        if (!miss) break;
        watchdog(n);
      }
      const uint4 v0 = tq < 2 ? own : sv[0], v1 = sv[1], v2 = sv[2], v3 = sv[3];
      PROF(8, ct == PT, 30); STAMP(6);
      float su = (__uint_as_float(v0.x) + __uint_as_float(v1.x)) + (__uint_as_float(v2.x) + __uint_as_float(v3.x));
      float sq = (__uint_as_float(v0.y) + __uint_as_float(v1.y)) + (__uint_as_float(v2.y) + __uint_as_float(v3.y));
      float dt = (__uint_as_float(v0.z) + __uint_as_float(v1.z)) + (__uint_as_float(v2.z) + __uint_as_float(v3.z));
      su += __shfl_xor_sync(0xffffffffu, su, 2); sq += __shfl_xor_sync(0xffffffffu, sq, 2); dt += __shfl_xor_sync(0xffffffffu, dt, 2);
      const float m = su * (1.f / DM);
      float mb, sd;
      ln_scalars(m, fmaxf(sq * (1.f / DM) - m * m, 0.f), mb, sd);
      const float inv = rcp(sd);
      rbest = (dt - mb * A1) * inv + A2;
      mm = pack_bf(mb, mb);
      ih = pack_bf(inv, inv);
      const float lo = inv - bf_lo(ih);
      il = pack_bf(lo, lo);
    }
    int ibest;
    {
      const uint32_t bits = __float_as_uint(rbest);
      const uint32_t key = (((int)bits < 0 ? ~bits : bits | 0x80000000u) & ~0x1ffu) | ((127 - lrow0 - (tq & 1) * 8) << 2) | tag;
      sts1(par + PAR_RED + warp * 4, __reduce_max_sync(0xffffffffu, key));
      PROF(8, ct == PT, 38); STAMP(7);
      bar_sync(1, 256);
      const uint4 ka = lds4(par + PAR_RED), kb = lds4(par + PAR_RED + 16);
      const uint32_t k2 = max(max(max(ka.x, ka.y), max(ka.z, ka.w)), max(max(kb.x, kb.y), max(kb.z, kb.w)));
      if (ct < CR && cj == 0) st_relaxed(g_cand + ct * 512 + rb * CS, k2);
      ibest = 127 - ((k2 >> 2) & 127);
    }
    PROF(8, ct == PT, 39); STAMP(8);
    if ((ibest >> 4) == warp) {
      const int src = (ibest & 7) * 4 + ((ibest >> 3) & 1), ch = g * 2;
      const uint32_t cm = __shfl_sync(0xffffffffu, mm, src), ch_ = __shfl_sync(0xffffffffu, ih, src), cl = __shfl_sync(0xffffffffu, il, src);
      const uint32_t xa = res + (ch >> 3) * 16384 + ibest * 128 + (((ch & 7) ^ (ibest & 7)) << 4) + tq * 4;
      const uint32_t x0 = lds1(xa), x1 = lds1(xa ^ 16);
      const uint2 p0 = lds2(par + PAR_T2 + ch * 64 + tq * 16), p1 = lds2(par + PAR_T2 + ch * 64 + 64 + tq * 16);
      uint32_t* dst = g_row + rb * 2 * DM + cj * 128 + ln * 4;
      st_pairs(dst, ln_mod(x0, cm, ch_, cl, p0.x, p0.y), ln_mod(x1, cm, ch_, cl, p1.x, p1.y), tag);
      st_pairs(dst + DM, x0, x1, tag);
      __syncwarp();
    }
    PROF(8, ct == PT, 37); STAMP(9);
    uint32_t wd[64];
    const uint32_t wda = base + unit_of(FT_D, warp >> 1) + (warp & 1) * 8192 + frow * 128 + ((((ln >> 3) & 1) ^ (ln & 7)) << 4);
#define LOAD_WD(f) ldmatrix4t((wda ^ ((((f) >> 1) & 3) * 32)) + ((f) >> 3) * 4096 + ((f) & 1) * 2048, wd[4 * (f)], wd[4 * (f) + 1], wd[4 * (f) + 2], wd[4 * (f) + 3])
    if (!early) {
      if (b < NFFN) mbar_wait(bar_box + (warp >> 1) * 8, 0);
      LOAD_WF(0);
      __syncwarp();
      mbar_arrive_pred(bar_gate, lane0);
    }
    if (b < NFFN) {
      const uint32_t own = base + unit_of(FT_G, warp >> 1) + (warp & 1) * 8192;
      mbar_wait(bar_box + (4 + (warp >> 1)) * 8, 0);
      LOAD_WF(1);
      uint32_t* const ydst = ypart_slot(b, warp * 16 + (tq & 1) * 8 + g);
      PROF(8, ct == PT, 31); STAMP(10);
      bool wdok;
      {
        uint32_t n = 0;
        while (!(wdok = __all_sync(0xffffffffu, mbar_test(bar_box + (8 + (warp >> 1)) * 8, 0))) && !__all_sync(0xffffffffu, mbar_test(bar_sel, 0))) watchdog(n);
      }
      if (wdok) {
#pragma unroll
        for (int f = 0; f < 16; f++) LOAD_WD(f);
      }
      STAMP(11);
      mbar_wait(bar_sel, 0);
      PROF(8, ct == PT, 33); STAMP(12);
      float d[8][4];
#pragma unroll
      for (int i = 0; i < 4; i++) { d[i][0] = 0.f; d[i][1] = 0.f; d[i][2] = 0.f; d[i][3] = 0.f; }
#pragma unroll
      for (int ks = 0; ks < 8; ks++) {
        const uint2 hb = lds2(own + 256 + ks * 32 + tq * 8);
#pragma unroll
        for (int mt = 0; mt < 4; mt++) {
          const int r = ks * 16 + mt * 4;
          mma16816(d[mt], wf[r], wf[r + 1], wf[r + 2], wf[r + 3], hb.x, hb.y);
        }
      }
      sts2(own + (tq * 8 + g) * 8, __float_as_uint((tq & 2) ? ((tq & 1) ? d[1][2] : d[1][0]) : ((tq & 1) ? d[0][2] : d[0][0])),
           __float_as_uint((tq & 2) ? ((tq & 1) ? d[3][2] : d[3][0]) : ((tq & 1) ? d[2][2] : d[2][0])));
      bar_sync(1, 256);
      uint32_t ab[4];
      {
        float G = 0.f, U = 0.f;
        uint2 pv[8];
#pragma unroll
        for (int w8 = 0; w8 < 8; w8++) pv[w8] = lds2(base + ln * 8 + ((FT_G >> (w8 >> 1) * 4) & 15) * UNIT + (w8 & 1) * 8192);
#pragma unroll
        for (int w8 = 0; w8 < 8; w8 += 2) {
          G += __uint_as_float(pv[w8].x) + __uint_as_float(pv[w8 + 1].x);
          U += __uint_as_float(pv[w8].y) + __uint_as_float(pv[w8 + 1].y);
        }
        const float act = rbf(silu_f(rbf(G))) * rbf(U);
        const uint32_t pk = pack_bf(act, __shfl_down_sync(0xffffffffu, act, 1));
#pragma unroll
        for (int i = 0; i < 4; i++) ab[i] = __shfl_sync(0xffffffffu, pk, i * 8 + tq * 2);
      }
      if (!wdok) {
        mbar_wait(bar_box + (8 + (warp >> 1)) * 8, 0);
#pragma unroll
        for (int f = 0; f < 16; f++) LOAD_WD(f);
      }
      PROF(8, ct == PT, 34); STAMP(13);
#pragma unroll
      for (int mt = 0; mt < 8; mt++) {
        d[mt][0] = 0.f; d[mt][1] = 0.f; d[mt][2] = 0.f; d[mt][3] = 0.f;
        mma16816(d[mt], wd[mt * 8], wd[mt * 8 + 1], wd[mt * 8 + 2], wd[mt * 8 + 3], ab[0], ab[1]);
        mma16816(d[mt], wd[mt * 8 + 4], wd[mt * 8 + 5], wd[mt * 8 + 6], wd[mt * 8 + 7], ab[2], ab[3]);
      }
      uint32_t yw[4];
#pragma unroll
      for (int i = 0; i < 4; i++) yw[i] = (tq & 1) ? pack_bf(d[2 * i][2], d[2 * i + 1][2]) : pack_bf(d[2 * i][0], d[2 * i + 1][0]);
      if (tq < 2) st_b128(ydst, (yw[0] & ~1u) | (tag & 1), (yw[1] & ~1u) | (tag >> 1), yw[2], yw[3]);
      PROF(8, ct == PT, 35); STAMP(14);
    }
    mbar_wait(bar_sel, 0);
    mbar_arrive_pred(bar_win, ct == 0);
    const int iwin = lds1(par + PAR_CONST + 60) & 0x7ff;
    const bool cand = (iwin >> 4) == rb * 8 + warp;
    {
      const uint32_t mm0 = __shfl_sync(0xffffffffu, mm, ln & ~1), mm1 = __shfl_sync(0xffffffffu, mm, ln | 1);
      const uint32_t ih0 = __shfl_sync(0xffffffffu, ih, ln & ~1), ih1 = __shfl_sync(0xffffffffu, ih, ln | 1);
      const uint32_t il0 = __shfl_sync(0xffffffffu, il, ln & ~1), il1 = __shfl_sync(0xffffffffu, il, ln | 1);
#pragma unroll 1
      for (int hf = 0; hf < 2; hf++) {
        uint32_t x[16];
#pragma unroll
        for (int i = 0; i < 8; i += 2) ldmatrix4((trow ^ (i << 4)) + hf * 16384, x[2 * i], x[2 * i + 1], x[2 * i + 2], x[2 * i + 3]);
#pragma unroll
        for (int i = 0; i < 8; i++) {
          const uint4 pv = lds4(par + PAR_T2 + (hf * 8 + i) * 64 + tq * 16);
          x[2 * i] = hfma2(hfma2(ln_norm(x[2 * i], mm0, ih0, il0), pv.x, pv.y), pv.z, x[2 * i]);
          x[2 * i + 1] = hfma2(hfma2(ln_norm(x[2 * i + 1], mm1, ih1, il1), pv.x, pv.y), pv.z, x[2 * i + 1]);
        }
#pragma unroll
        for (int i = 0; i < 8; i += 2) stmatrix4((trow ^ (i << 4)) + hf * 16384, x[2 * i], x[2 * i + 1], x[2 * i + 2], x[2 * i + 3]);
        if (!cand) fence_async_smem();
        __syncwarp();
        if (!cand && elect_one()) {
          tma2d_store(&maps.out, res + hf * 16384 + warp * 2048, cj * 128 + hf * 64, rb * 128 + warp * 16);
          asm volatile("cp.async.bulk.commit_group;" ::: "memory");
        }
      }
    }
    if (cand) {
      const int wrow0 = warp * 16;
#pragma unroll 2
      for (int p = 0; p < 8; p++) {
        const int row = 2 * p + (ln >> 4), ch = ln & 15;
        const uint4 v = lds4(res + (ch >> 3) * 16384 + (wrow0 + row) * 128 + (((ch & 7) ^ (row & 7)) << 4));
        if (rb * 128 + wrow0 + row != iwin) *reinterpret_cast<uint4*>(P.out + (size_t)(rb * 128 + wrow0 + row) * DM + cj * 128 + ch * 8) = v;
      }
    }
    asm volatile("cp.async.bulk.wait_group.read 0;" ::: "memory");
    PROF(8, ct == PT, 11); STAMP(15);
    cluster_wait();
  }
}

typedef CUresult (*EncodeFn)(CUtensorMap*, CUtensorMapDataType, cuuint32_t, void*, const cuuint64_t*, const cuuint64_t*,
                             const cuuint32_t*, const cuuint32_t*, CUtensorMapInterleave, CUtensorMapSwizzle,
                             CUtensorMapL2promotion, CUtensorMapFloatOOBfill);

void map2d(EncodeFn enc, CUtensorMap* m, const void* p, uint64_t rows, uint64_t cols, uint32_t brows) {
  cuuint64_t dims[2] = {cols, rows}, strides[1] = {cols * 2};
  cuuint32_t box[2] = {64, brows}, es[2] = {1, 1};
  enc(m, CU_TENSOR_MAP_DATA_TYPE_BFLOAT16, 2, const_cast<void*>(p), dims, strides, box, es, CU_TENSOR_MAP_INTERLEAVE_NONE,
      CU_TENSOR_MAP_SWIZZLE_128B, CU_TENSOR_MAP_L2_PROMOTION_L2_256B, CU_TENSOR_MAP_FLOAT_OOB_FILL_NONE);
}
void map2d_narrow(EncodeFn enc, CUtensorMap* m, const void* p, uint64_t rows, uint64_t cols, uint32_t brows) {
  cuuint64_t dims[2] = {cols, rows}, strides[1] = {cols * 2};
  cuuint32_t box[2] = {32, brows}, es[2] = {1, 1};
  enc(m, CU_TENSOR_MAP_DATA_TYPE_BFLOAT16, 2, const_cast<void*>(p), dims, strides, box, es, CU_TENSOR_MAP_INTERLEAVE_NONE,
      CU_TENSOR_MAP_SWIZZLE_64B, CU_TENSOR_MAP_L2_PROMOTION_L2_64B, CU_TENSOR_MAP_FLOAT_OOB_FILL_NONE);
}
void map3d(EncodeFn enc, CUtensorMap* m, const void* p, uint64_t rows, uint64_t cols, uint32_t brows, uint32_t nch) {
  cuuint64_t dims[3] = {64, rows, cols / 64}, strides[2] = {cols * 2, 128};
  cuuint32_t box[3] = {64, brows, nch}, es[3] = {1, 1, 1};
  enc(m, CU_TENSOR_MAP_DATA_TYPE_BFLOAT16, 3, const_cast<void*>(p), dims, strides, box, es, CU_TENSOR_MAP_INTERLEAVE_NONE,
      CU_TENSOR_MAP_SWIZZLE_128B, CU_TENSOR_MAP_L2_PROMOTION_L2_256B, CU_TENSOR_MAP_FLOAT_OOB_FILL_NONE);
}

}

extern "C" void kernel_launch(void* const* d_in, const int* in_sizes, int n_in, void* d_out, int out_size) {
  (void)in_sizes; (void)n_in; (void)out_size;
  static EncodeFn enc = nullptr;
  if (!enc) {
    void* fn = nullptr;
    cudaDriverEntryPointQueryResult st;
    cudaGetDriverEntryPoint("cuTensorMapEncodeTiled", &fn, cudaEnableDefault, &st);
    enc = (EncodeFn)fn;
    cudaFuncSetAttribute(fused_kernel, cudaFuncAttributeMaxDynamicSharedMemorySize, SMEM_BYTES);
  }
  Maps maps;
  map2d(enc, &maps.x, d_in[0], SEQ, DM, 128);
  map2d(enc, &maps.out, d_out, SEQ, DM, 16);
  map3d(enc, &maps.wq, d_in[3], DM, NQ, 64, 2);
  map3d(enc, &maps.k, d_in[1], 4 * SK, 128, 128, 1);
  map3d(enc, &maps.v, d_in[2], 4 * SK, 128, 128, 1);
  map3d(enc, &maps.wo, d_in[4], NQ, DM, 64, 2);
  map2d_narrow(enc, &maps.wg, d_in[7], DM, FF, 256);
  map2d_narrow(enc, &maps.wu, d_in[8], DM, FF, 256);
  map3d(enc, &maps.wd, d_in[9], FF, DM, 32, 4);
  map2d_narrow(enc, &maps.wm, d_in[11], DM, NMOD, 256);
  Ptrs p;
  p.x = (const __nv_bfloat16*)d_in[0];
  p.w_r = (const __nv_bfloat16*)d_in[6];
  p.w_gate = (const __nv_bfloat16*)d_in[7];
  p.w_up = (const __nv_bfloat16*)d_in[8];
  p.w_down = (const __nv_bfloat16*)d_in[9];
  p.c = (const __nv_bfloat16*)d_in[10];
  p.w_mod = (const __nv_bfloat16*)d_in[11];
  p.out = (__nv_bfloat16*)d_out;
  fused_kernel<<<NMAIN + NHELP, 384, SMEM_BYTES>>>(maps, p);
}
```

```cpp
#include <cuda_runtime.h>
#include <cuda_bf16.h>
#include <cuda.h>
#include <stdint.h>
#include <type_traits>

#define HD 2
#define HDX 2
#define NRS 8
#define OSL 900
#define OSL2 400
#define RSL 40
#define VREL 5
#define OPS 8192
#define ODS1 5
#define ODS 7
#define PG0 15
#define WB 2
#define WN 20
#define HU 32
#define RES0 17
#define RES1 20
#define GOST 20
#define NS1 5
#define LD2 4
#define FPACE0 2
#define FPACE 3
#define CR 8
#define CS 8

namespace {

constexpr int SEQ = 2048, DM = 1024, NQ = 4096, SK = 2048, WIN = 512, FF = 3584, NMOD = 6144;
constexpr int NMAIN = 128, NHELP = 4, NFFN = 112;
constexpr int NSLOT = 4, SLOT_BYTES = 32768, UNIT = 16384, GST_BYTES = 3 * UNIT;
constexpr uint32_t XT1 = 0xDCBA, XT2 = 0x9687;
constexpr uint32_t WT0 = 0xA741, WT1 = 0x7420, WT2 = 0x4A20;
constexpr uint32_t AT0 = WT1, AT1 = WT2;
constexpr uint32_t QT = 0xDC9696DC;
constexpr int OFF_STAGE = 12 * UNIT;
constexpr uint32_t FT_G = 0x07B3, FT_U = 0xA628, FT_D = 0x5149;
constexpr int OFF_RES = 12 * UNIT;
constexpr int OFF_PAR = 14 * UNIT;
constexpr int OFF_BAR = OFF_PAR + 2528;
constexpr int SMEM_BYTES = OFF_BAR + 544;
static_assert(SMEM_BYTES <= 232448, "smem");

constexpr int PAR_T1 = 0;
constexpr int PAR_T2 = 512;
constexpr int PAR_CONST = 1536;
constexpr int PAR_RED = 1600;
constexpr int PAR_SINK = 2176;

struct Maps {
  CUtensorMap x, wq, k, v, wo, wg, wu, wd, wm, out;
};
struct Ptrs {
  const __nv_bfloat16 *x, *w_r, *c, *w_mod, *w_gate, *w_up, *w_down;
  __nv_bfloat16* out;
};

__device__ __align__(1024) uint8_t g_act[16 * 80 * UNIT];
__device__ __align__(128) uint32_t g_mod[NMOD];
__device__ __align__(128) uint32_t g_modp[2 * 2 * DM];
__device__ __align__(128) uint32_t g_ln1[SEQ * 4];
__device__ __align__(128) uint32_t g_cnt_h[16 * 32];
__device__ __align__(128) uint32_t g_cnt_o[128 * 32];
__device__ __align__(128) uint32_t g_xch[NMAIN * 8 * 256 * 4];
__device__ __align__(128) uint32_t g_stats[8 * SEQ * 4];
__device__ __align__(128) uint32_t g_cand[CR * 512];
__device__ __align__(128) uint32_t g_row[16 * 2 * DM];
__device__ __align__(128) uint32_t g_ypart[NMAIN * NFFN * 4];
__device__ __forceinline__ uint32_t* ypart_slot(int writer, int reader) { return g_ypart + (writer * NMAIN + reader) * 4; }
__device__ uint32_t g_epoch;

__device__ __forceinline__ uint32_t fresh_lane() { uint32_t l; asm volatile("mov.u32 %0, %%laneid;" : "=r"(l)); return l; }
__device__ __forceinline__ uint32_t frag_offset(int warp) {
  const uint32_t l = fresh_lane();
  return ((warp & 3) * 16 + (l & 15)) * 128 + (((l >> 4) ^ (l & 7)) << 4);
}
__device__ __forceinline__ bool elect_one() {
  uint32_t p;
  asm volatile("{ .reg .pred q; elect.sync _|q, 0xffffffff; selp.u32 %0, 1, 0, q; }" : "=r"(p));
  return p;
}
__device__ __forceinline__ uint32_t smem_u32(const void* p) { return (uint32_t)__cvta_generic_to_shared(p); }
__device__ __forceinline__ void mbar_init(uint32_t bar, uint32_t cnt) {
  asm volatile("mbarrier.init.shared::cta.b64 [%0], %1;" ::"r"(bar), "r"(cnt) : "memory");
}
__device__ __forceinline__ void mbar_expect_tx(uint32_t bar, uint32_t bytes) {
  asm volatile("mbarrier.arrive.expect_tx.shared::cta.b64 _, [%0], %1;" ::"r"(bar), "r"(bytes) : "memory");
}
__device__ __forceinline__ void mbar_arrive(uint32_t bar) {
  asm volatile("mbarrier.arrive.shared::cta.b64 _, [%0];" ::"r"(bar) : "memory");
}
__device__ __forceinline__ void mbar_arrive_pred(uint32_t bar, bool p) {
  asm volatile("{ .reg .pred p; setp.ne.b32 p, %1, 0; @p mbarrier.arrive.shared::cta.b64 _, [%0]; }" ::"r"(bar), "r"((int)p) : "memory");
}
__device__ __forceinline__ void mbar_arrive_cl(uint32_t bar, uint32_t off, bool p = true) {
  asm volatile("{ .reg .pred p, q; .reg .b32 a; setp.ne.b32 q, %2, 0; setp.ne.and.b32 p, %0, 0, q; add.u32 a, %0, %1; @p mbarrier.arrive.shared::cluster.b64 _, [a]; }"
               ::"r"(bar), "r"(off), "r"((int)p) : "memory");
}
__device__ __forceinline__ uint32_t mapa(uint32_t addr, uint32_t cta) {
  uint32_t r; asm("mapa.shared::cluster.u32 %0, %1, %2;" : "=r"(r) : "r"(addr), "r"(cta)); return r;
}
__device__ __forceinline__ void cluster_arrive() { asm volatile("barrier.cluster.arrive.relaxed.aligned;" ::: "memory"); }
__device__ __forceinline__ void cluster_wait() { asm volatile("barrier.cluster.wait.aligned;" ::: "memory"); }
__device__ __forceinline__ void watchdog(uint32_t& n) {
}
__device__ __forceinline__ void mbar_wait(uint32_t bar, uint32_t parity) {
  asm volatile("{\n.reg .pred p;\nWAIT_%=:\nmbarrier.try_wait.parity.shared::cta.b64 p, [%0], %1;\n@!p bra WAIT_%=;\n}" ::"r"(bar), "r"(parity) : "memory");
}
__device__ __forceinline__ bool mbar_test(uint32_t bar, uint32_t parity) {
  uint32_t ok;
  asm volatile("{\n.reg .pred p;\nmbarrier.test_wait.parity.shared::cta.b64 p, [%1], %2;\nselp.u32 %0, 1, 0, p;\n}" : "=r"(ok) : "r"(bar), "r"(parity) : "memory");
  return ok;
}
__device__ __forceinline__ uint64_t l2_stream() {
  uint64_t f; asm("createpolicy.fractional.L2::evict_first.b64 %0, 1.0;" : "=l"(f)); return f;
}
__device__ __forceinline__ uint64_t l2_normal() {
  uint64_t f; asm("createpolicy.fractional.L2::evict_normal.b64 %0, 1.0;" : "=l"(f)); return f;
}
__device__ __forceinline__ void tma2d(uint32_t dst, const CUtensorMap* m, int c0, int c1, uint32_t bar) {
  asm volatile("cp.async.bulk.tensor.2d.shared::cluster.global.mbarrier::complete_tx::bytes.L2::cache_hint [%0], [%1, {%3, %4}], [%2], %5;"
               ::"r"(dst), "l"(m), "r"(bar), "r"(c0), "r"(c1), "l"(l2_stream()) : "memory");
}
__device__ __forceinline__ void bulk_load(uint32_t dst, const void* src, uint32_t bytes, uint32_t bar) {
  asm volatile("cp.async.bulk.shared::cluster.global.mbarrier::complete_tx::bytes [%0], [%1], %2, [%3];" ::"r"(dst), "l"(src), "r"(bytes), "r"(bar) : "memory");
}
__device__ __forceinline__ void bulk_load_stream(uint32_t dst, const void* src, uint32_t bytes, uint32_t bar, uint64_t pol = l2_stream()) {
  asm volatile("cp.async.bulk.shared::cluster.global.mbarrier::complete_tx::bytes.L2::cache_hint [%0], [%1], %2, [%3], %4;"
               ::"r"(dst), "l"(src), "r"(bytes), "r"(bar), "l"(pol) : "memory");
}
__device__ __forceinline__ void tma2d_store(const CUtensorMap* m, uint32_t src, int c0, int c1) {
  asm volatile("cp.async.bulk.tensor.2d.global.shared::cta.bulk_group [%0, {%2, %3}], [%1];" ::"l"(m), "r"(src), "r"(c0), "r"(c1) : "memory");
}
__device__ __forceinline__ void bulk_store(void* dst, uint32_t src, uint32_t bytes) {
  asm volatile("cp.async.bulk.global.shared::cta.bulk_group [%0], [%1], %2;" ::"l"(dst), "r"(src), "r"(bytes) : "memory");
}
__device__ __forceinline__ int slice_of(int i) { return i + ((i & 7) == 1) - ((i & 7) == 2); }
__device__ __forceinline__ uint32_t unit_of(uint32_t table, uint32_t i) { return ((table >> (i * 4)) & 15) * UNIT; }
__device__ __forceinline__ void tma3d(uint32_t dst, const CUtensorMap* m, int c0, int c1, int c2, uint32_t bar) {
  asm volatile("cp.async.bulk.tensor.3d.shared::cluster.global.mbarrier::complete_tx::bytes.L2::cache_hint [%0], [%1, {%3, %4, %5}], [%2], %6;"
               ::"r"(dst), "l"(m), "r"(bar), "r"(c0), "r"(c1), "r"(c2), "l"(l2_stream()) : "memory");
}
template <bool STREAM>
__device__ __forceinline__ void tma3d_mc(uint32_t dst, const CUtensorMap* m, int c0, int c1, int c2, uint32_t bar) {
  if (STREAM)
    asm volatile("cp.async.bulk.tensor.3d.shared::cluster.global.mbarrier::complete_tx::bytes.multicast::cluster.L2::cache_hint [%0], [%1, {%3, %4, %5}], [%2], %6, %7;"
                 ::"r"(dst), "l"(m), "r"(bar), "r"(c0), "r"(c1), "r"(c2), "h"((uint16_t)3), "l"(l2_stream()) : "memory");
  else
    asm volatile("cp.async.bulk.tensor.3d.shared::cluster.global.mbarrier::complete_tx::bytes.multicast::cluster [%0], [%1, {%3, %4, %5}], [%2], %6;"
                 ::"r"(dst), "l"(m), "r"(bar), "r"(c0), "r"(c1), "r"(c2), "h"((uint16_t)3) : "memory");
}
__device__ __forceinline__ void prefetch_map(const CUtensorMap* m) {
  asm volatile("prefetch.tensormap [%0];" ::"l"(m) : "memory");
}
__device__ __forceinline__ void fence_async() { asm volatile("fence.proxy.async.global;" ::: "memory"); }
__device__ __forceinline__ void fence_async_smem() { asm volatile("fence.proxy.async.shared::cta;" ::: "memory"); }
__device__ __forceinline__ void bar_sync(int id, int n) { asm volatile("bar.sync %0, %1;" ::"r"(id), "r"(n) : "memory"); }
__device__ __forceinline__ void bar_arrive(int id, int n) { asm volatile("bar.arrive %0, %1;" ::"r"(id), "r"(n) : "memory"); }
__device__ __forceinline__ void wg_fence() { asm volatile("wgmma.fence.sync.aligned;" ::: "memory"); }
__device__ __forceinline__ void wg_commit() { asm volatile("wgmma.commit_group.sync.aligned;" ::: "memory"); }
template <int N> __device__ __forceinline__ void wg_wait() { asm volatile("wgmma.wait_group.sync.aligned %0;" ::"n"(N) : "memory"); }
__device__ __forceinline__ uint64_t make_desc(uint32_t addr, uint32_t lbo, uint32_t sbo) {
  return (uint64_t)((addr & 0x3FFFF) >> 4) | ((uint64_t)(lbo >> 4) << 16) | ((uint64_t)(sbo >> 4) << 32) | (1ull << 62);
}
__device__ __forceinline__ uint32_t ld_relaxed(const uint32_t* p) {
  uint32_t v; asm volatile("ld.relaxed.gpu.global.u32 %0, [%1];" : "=r"(v) : "l"(p) : "memory"); return v;
}
__device__ __forceinline__ uint32_t ld_acquire(const uint32_t* p) {
  uint32_t v; asm volatile("ld.acquire.gpu.global.u32 %0, [%1];" : "=r"(v) : "l"(p) : "memory"); return v;
}
__device__ __forceinline__ uint4 ld_relaxed4(const uint32_t* p) {
  uint4 v; asm volatile("ld.relaxed.gpu.global.v4.u32 {%0,%1,%2,%3}, [%4];" : "=r"(v.x), "=r"(v.y), "=r"(v.z), "=r"(v.w) : "l"(p) : "memory"); return v;
}
__device__ __forceinline__ void st_relaxed(uint32_t* p, uint32_t v) {
  asm volatile("st.relaxed.gpu.global.u32 [%0], %1;" ::"l"(p), "r"(v) : "memory");
}
__device__ __forceinline__ void st_relaxed4(uint32_t* p, uint32_t a, uint32_t b, uint32_t c, uint32_t d) {
  asm volatile("st.relaxed.gpu.global.v4.u32 [%0], {%1,%2,%3,%4};" ::"l"(p), "r"(a), "r"(b), "r"(c), "r"(d) : "memory");
}
__device__ __forceinline__ void st_b128(uint32_t* p, uint32_t a, uint32_t b, uint32_t c, uint32_t d) {
  asm volatile("{ .reg .b64 u, v; .reg .b128 w; mov.b64 u, {%1, %2}; mov.b64 v, {%3, %4}; mov.b128 w, {u, v}; st.relaxed.gpu.global.b128 [%0], w; }"
               ::"l"(p), "r"(a), "r"(b), "r"(c), "r"(d) : "memory");
}
__device__ __forceinline__ uint4 ld_b128(const uint32_t* p) {
  uint4 r;
  asm volatile("{ .reg .b64 u, v; .reg .b128 w; ld.relaxed.gpu.global.b128 w, [%4]; mov.b128 {u, v}, w; mov.b64 {%0, %1}, u; mov.b64 {%2, %3}, v; }"
               : "=r"(r.x), "=r"(r.y), "=r"(r.z), "=r"(r.w) : "l"(p) : "memory");
  return r;
}
__device__ __forceinline__ void st_pairs(uint32_t* p, uint32_t a, uint32_t b, uint32_t tag) {
  asm volatile("{ .reg .b64 u, v; mov.b64 u, {%1, %3}; mov.b64 v, {%2, %3}; st.relaxed.gpu.global.v2.b64 [%0], {u, v}; }"
               ::"l"(p), "r"(a), "r"(b), "r"(tag) : "memory");
}
__device__ __forceinline__ uint4 ld_pairs(const uint32_t* p) {
  uint4 v;
  asm volatile("{ .reg .b64 u, v; ld.relaxed.gpu.global.v2.b64 {u, v}, [%4]; mov.b64 {%0, %1}, u; mov.b64 {%2, %3}, v; }"
               : "=r"(v.x), "=r"(v.y), "=r"(v.z), "=r"(v.w) : "l"(p) : "memory");
  return v;
}
__device__ __forceinline__ uint2 ld_pair(const uint32_t* p) {
  uint2 v;
  asm volatile("{ .reg .b64 u; ld.relaxed.gpu.global.b64 u, [%2]; mov.b64 {%0, %1}, u; }" : "=r"(v.x), "=r"(v.y) : "l"(p) : "memory");
  return v;
}
__device__ __forceinline__ void red_release(uint32_t* p, uint32_t v) {
  asm volatile("red.release.gpu.global.add.u32 [%0], %1;" ::"l"(p), "r"(v) : "memory");
}
__device__ __forceinline__ uint32_t ldg_nc1(const void* p) {
  uint32_t v;
  asm volatile("ld.global.nc.u32 %0, [%1];" : "=r"(v) : "l"(p));
  return v;
}
__device__ __forceinline__ uint4 ldg_nc4(const void* p) {
  uint4 v; asm volatile("ld.global.nc.L1::no_allocate.v4.u32 {%0,%1,%2,%3}, [%4];" : "=r"(v.x), "=r"(v.y), "=r"(v.z), "=r"(v.w) : "l"(p)); return v;
}
__device__ __forceinline__ uint4 ldg_stream4(const void* p) {
  uint4 v;
  asm volatile("ld.global.nc.L1::no_allocate.L2::cache_hint.v4.u32 {%0,%1,%2,%3}, [%4], %5;" : "=r"(v.x), "=r"(v.y), "=r"(v.z), "=r"(v.w) : "l"(p), "l"(l2_stream()));
  return v;
}
__device__ __forceinline__ void stg4(void* p, uint4 v) {
  asm volatile("st.global.v4.u32 [%0], {%1,%2,%3,%4};" ::"l"(p), "r"(v.x), "r"(v.y), "r"(v.z), "r"(v.w) : "memory");
}
__device__ __forceinline__ void wait_counter(const uint32_t* p, uint32_t target) {
  uint32_t n = 0;
  while (__any_sync(0xffffffffu, (int)(ld_acquire(p) - target) < 0)) { watchdog(n); }
}
__device__ __forceinline__ uint32_t tagf(float v, uint32_t tag) { return (__float_as_uint(v) & ~3u) | tag; }
__device__ __forceinline__ bool tag_ok(uint4 v, uint32_t tag) { return (((v.x ^ tag) | (v.y ^ tag) | (v.z ^ tag) | (v.w ^ tag)) & 3u) == 0; }
__device__ __forceinline__ float untag_sum(uint32_t a, uint32_t b) { return __uint_as_float(a & ~3u) + __uint_as_float(b & ~3u); }
__device__ __forceinline__ uint4 poll4(const uint32_t* p, uint32_t tag) {
  uint4 v = ld_relaxed4(p);
  uint32_t n = 0;
  while (!__all_sync(0xffffffffu, tag_ok(v, tag))) { v = ld_relaxed4(p); watchdog(n); }
  return v;
}
__device__ __forceinline__ float bf_lo(uint32_t v) { return __uint_as_float(v << 16); }
__device__ __forceinline__ float bf_hi(uint32_t v) { return __uint_as_float(v & 0xffff0000u); }
__device__ __forceinline__ uint32_t pack_bf(float lo, float hi) {
  uint32_t r; asm("cvt.rn.bf16x2.f32 %0, %1, %2;" : "=r"(r) : "f"(hi), "f"(lo)); return r;
}
__device__ __forceinline__ float rbf(float v) { return __uint_as_float(pack_bf(0.f, v) & 0xffff0000u); }
__device__ __forceinline__ uint32_t hmul2(uint32_t a, uint32_t b) {
  uint32_t r; asm("mul.rn.bf16x2 %0, %1, %2;" : "=r"(r) : "r"(a), "r"(b)); return r;
}
__device__ __forceinline__ uint32_t hadd2(uint32_t a, uint32_t b) {
  uint32_t r; asm("add.rn.bf16x2 %0, %1, %2;" : "=r"(r) : "r"(a), "r"(b)); return r;
}
__device__ __forceinline__ uint32_t hsub2(uint32_t a, uint32_t b) {
  uint32_t r; asm("sub.rn.bf16x2 %0, %1, %2;" : "=r"(r) : "r"(a), "r"(b)); return r;
}
__device__ __forceinline__ float rcp(float x) { float r; asm("rcp.approx.ftz.f32 %0, %1;" : "=f"(r) : "f"(x)); return r; }
__device__ __forceinline__ float ex2(float x) { float r; asm("ex2.approx.ftz.f32 %0, %1;" : "=f"(r) : "f"(x)); return r; }
__device__ __forceinline__ void stmatrix4(uint32_t addr, uint32_t a, uint32_t b, uint32_t c, uint32_t d) {
  asm volatile("stmatrix.sync.aligned.m8n8.x4.shared.b16 [%0], {%1,%2,%3,%4};" ::"r"(addr), "r"(a), "r"(b), "r"(c), "r"(d) : "memory");
}
__device__ __forceinline__ void ldmatrix4(uint32_t addr, uint32_t& a, uint32_t& b, uint32_t& c, uint32_t& d) {
  asm volatile("ldmatrix.sync.aligned.m8n8.x4.shared.b16 {%0,%1,%2,%3}, [%4];" : "=r"(a), "=r"(b), "=r"(c), "=r"(d) : "r"(addr) : "memory");
}
__device__ __forceinline__ void ldmatrix4t(uint32_t addr, uint32_t& a, uint32_t& b, uint32_t& c, uint32_t& d) {
  asm volatile("ldmatrix.sync.aligned.m8n8.x4.trans.shared.b16 {%0,%1,%2,%3}, [%4];" : "=r"(a), "=r"(b), "=r"(c), "=r"(d) : "r"(addr) : "memory");
}
__device__ __forceinline__ void mma16816(float (&d)[4], uint32_t a0, uint32_t a1, uint32_t a2, uint32_t a3, uint32_t b0, uint32_t b1) {
  asm volatile("mma.sync.aligned.m16n8k16.row.col.f32.bf16.bf16.f32 {%0,%1,%2,%3}, {%4,%5,%6,%7}, {%8,%9}, {%0,%1,%2,%3};"
               : "+f"(d[0]), "+f"(d[1]), "+f"(d[2]), "+f"(d[3]) : "r"(a0), "r"(a1), "r"(a2), "r"(a3), "r"(b0), "r"(b1));
}
__device__ __forceinline__ void sts1(uint32_t a, uint32_t v) { asm volatile("st.shared.u32 [%0], %1;" ::"r"(a), "r"(v) : "memory"); }
__device__ __forceinline__ uint4 lds4(uint32_t a) {
  uint4 v; asm volatile("ld.shared.v4.u32 {%0,%1,%2,%3}, [%4];" : "=r"(v.x), "=r"(v.y), "=r"(v.z), "=r"(v.w) : "r"(a) : "memory"); return v;
}
__device__ __forceinline__ uint2 lds2(uint32_t a) {
  uint2 v; asm volatile("ld.shared.v2.u32 {%0,%1}, [%2];" : "=r"(v.x), "=r"(v.y) : "r"(a) : "memory"); return v;
}
__device__ __forceinline__ uint32_t lds1(uint32_t a) {
  uint32_t v; asm volatile("ld.shared.u32 %0, [%1];" : "=r"(v) : "r"(a) : "memory"); return v;
}
__device__ __forceinline__ void sts2(uint32_t a, uint32_t x, uint32_t y) { asm volatile("st.shared.v2.u32 [%0], {%1,%2};" ::"r"(a), "r"(x), "r"(y) : "memory"); }
__device__ __forceinline__ void sts4(uint32_t a, uint4 v) {
  asm volatile("st.shared.v4.u32 [%0], {%1,%2,%3,%4};" ::"r"(a), "r"(v.x), "r"(v.y), "r"(v.z), "r"(v.w) : "memory");
}
__device__ __forceinline__ float silu_f(float v) { return __fdividef(v, 1.f + __expf(-v)); }
__device__ __forceinline__ uint32_t hfma2(uint32_t a, uint32_t b, uint32_t c) {
  uint32_t r; asm("fma.rn.bf16x2 %0, %1, %2, %3;" : "=r"(r) : "r"(a), "r"(b), "r"(c)); return r;
}
__device__ __forceinline__ void split_inv(float sd, uint32_t& ih, uint32_t& il) {
  const float inv = rcp(sd);
  ih = pack_bf(inv, inv);
  const float lo = inv - bf_lo(ih);
  il = pack_bf(lo, lo);
}
__device__ __forceinline__ uint32_t ln_norm(uint32_t x, uint32_t mean2, uint32_t ih, uint32_t il) {
  const uint32_t d = hsub2(x, mean2);
  return hfma2(d, ih, hmul2(d, il));
}
__device__ __forceinline__ uint32_t ln_mod(uint32_t x, uint32_t mean2, uint32_t ih, uint32_t il, uint32_t c1, uint32_t sh) {
  return hadd2(hmul2(ln_norm(x, mean2, ih, il), c1), sh);
}

#define R8(a, i) "+f"(a[i]), "+f"(a[i + 1]), "+f"(a[i + 2]), "+f"(a[i + 3]), "+f"(a[i + 4]), "+f"(a[i + 5]), "+f"(a[i + 6]), "+f"(a[i + 7])
#define D64 "{%0,%1,%2,%3,%4,%5,%6,%7,%8,%9,%10,%11,%12,%13,%14,%15,%16,%17,%18,%19,%20,%21,%22,%23,%24,%25,%26,%27,%28,%29,%30,%31," \
            "%32,%33,%34,%35,%36,%37,%38,%39,%40,%41,%42,%43,%44,%45,%46,%47,%48,%49,%50,%51,%52,%53,%54,%55,%56,%57,%58,%59,%60,%61,%62,%63}"
template <int TB>
__device__ __forceinline__ void mma_ss(float (&d)[64], uint64_t da, uint64_t db, int sc) {
  asm volatile("{\n.reg .pred p;\nsetp.ne.b32 p, %66, 0;\n"
               "wgmma.mma_async.sync.aligned.m64n128k16.f32.bf16.bf16 " D64 ", %64, %65, p, 1, 1, 0, %67;\n}"
               : R8(d, 0), R8(d, 8), R8(d, 16), R8(d, 24), R8(d, 32), R8(d, 40), R8(d, 48), R8(d, 56)
               : "l"(da), "l"(db), "r"(sc), "n"(TB));
}
template <int TB>
__device__ __forceinline__ void mma_rs(float (&d)[64], uint32_t a0, uint32_t a1, uint32_t a2, uint32_t a3, uint64_t db, int sc) {
  asm volatile("{\n.reg .pred p;\nsetp.ne.b32 p, %69, 0;\n"
               "wgmma.mma_async.sync.aligned.m64n128k16.f32.bf16.bf16 " D64 ", {%64,%65,%66,%67}, %68, p, 1, 1, %70;\n}"
               : R8(d, 0), R8(d, 8), R8(d, 16), R8(d, 24), R8(d, 32), R8(d, 40), R8(d, 48), R8(d, 56)
               : "r"(a0), "r"(a1), "r"(a2), "r"(a3), "l"(db), "r"(sc), "n"(TB));
}
#define D128 "{%0,%1,%2,%3,%4,%5,%6,%7,%8,%9,%10,%11,%12,%13,%14,%15,%16,%17,%18,%19,%20,%21,%22,%23,%24,%25,%26,%27,%28,%29,%30,%31," \
             "%32,%33,%34,%35,%36,%37,%38,%39,%40,%41,%42,%43,%44,%45,%46,%47,%48,%49,%50,%51,%52,%53,%54,%55,%56,%57,%58,%59,%60,%61,%62,%63," \
             "%64,%65,%66,%67,%68,%69,%70,%71,%72,%73,%74,%75,%76,%77,%78,%79,%80,%81,%82,%83,%84,%85,%86,%87,%88,%89,%90,%91,%92,%93,%94,%95," \
             "%96,%97,%98,%99,%100,%101,%102,%103,%104,%105,%106,%107,%108,%109,%110,%111,%112,%113,%114,%115,%116,%117,%118,%119,%120,%121,%122,%123,%124,%125,%126,%127}"
#define R128(d, e) R8(d, 0), R8(d, 8), R8(d, 16), R8(d, 24), R8(d, 32), R8(d, 40), R8(d, 48), R8(d, 56), \
                   R8(e, 0), R8(e, 8), R8(e, 16), R8(e, 24), R8(e, 32), R8(e, 40), R8(e, 48), R8(e, 56)
__device__ __forceinline__ void mma256_ss(float (&d)[64], float (&e)[64], uint64_t da, uint64_t db, int sc) {
  asm volatile("{\n.reg .pred p;\nsetp.ne.b32 p, %130, 0;\n"
               "wgmma.mma_async.sync.aligned.m64n256k16.f32.bf16.bf16 " D128 ", %128, %129, p, 1, 1, 0, 1;\n}"
               : R128(d, e) : "l"(da), "l"(db), "r"(sc));
}
__device__ __forceinline__ void mma256_rs(float (&d)[64], float (&e)[64], uint32_t a0, uint32_t a1, uint32_t a2, uint32_t a3, uint64_t db) {
  asm volatile("{\n.reg .pred p;\nsetp.ne.b32 p, 1, 0;\n"
               "wgmma.mma_async.sync.aligned.m64n256k16.f32.bf16.bf16 " D128 ", {%128,%129,%130,%131}, %132, p, 1, 1, 1;\n}"
               : R128(d, e) : "r"(a0), "r"(a1), "r"(a2), "r"(a3), "l"(db));
}
template <int N> __device__ __forceinline__ void keep(float (&a)[N]) {
#pragma unroll
  for (int i = 0; i < N; i++) asm volatile("" : "+f"(a[i])::"memory");
}
template <int N> __device__ __forceinline__ void keep(uint32_t (&a)[N]) {
#pragma unroll
  for (int i = 0; i < N; i++) asm volatile("" : "+r"(a[i])::"memory");
}

#define STAMP(idx) do {} while (0)
#define PROF(grp, cond, idx) do {} while (0)

constexpr float SCL2 = 1.4426950408889634f * 0.08838834764831845f;

__device__ __forceinline__ void pack_p(const float (&s)[64], uint32_t (&p)[32]) {
#pragma unroll
  for (int i = 0; i < 32; i++) p[i] = pack_bf(s[2 * i], s[2 * i + 1]);
}

__device__ __forceinline__ void issue_qk(float (&s)[64], uint32_t q0, uint32_t q1, uint32_t kslot) {
  const uint64_t db = make_desc(kslot, 16, 1024), da0 = make_desc(q0, 16, 1024), da1 = make_desc(q1, 16, 1024);
#pragma unroll
  for (int kk = 0; kk < 8; kk++) mma_ss<0>(s, (kk < 4 ? da0 : da1) + (kk & 3) * 2, db + (kk >> 2) * 1024 + (kk & 3) * 2, kk != 0);
}
__device__ __forceinline__ void issue_pv(float (&o)[64], uint32_t (&p)[32], uint32_t vslot, int acc) {
  uint64_t db = make_desc(vslot, 16384, 1024);
#pragma unroll
  for (int kk = 0; kk < 8; kk++)
    mma_rs<1>(o, p[4 * kk], p[4 * kk + 1], p[4 * kk + 2], p[4 * kk + 3], db + kk * 128, kk == 0 ? acc : 1);
}

template <int H>
__device__ __forceinline__ void store_chunk(const float (&a)[64], uint32_t addr) {
#pragma unroll
  for (int i = 8 * H; i < 8 * H + 8; i += 2)
    stmatrix4(addr ^ ((i & 7) << 4), pack_bf(a[4 * i], a[4 * i + 1]), pack_bf(a[4 * i + 2], a[4 * i + 3]),
              pack_bf(a[4 * i + 4], a[4 * i + 5]), pack_bf(a[4 * i + 6], a[4 * i + 7]));
}
template <int H>
__device__ __forceinline__ void store_chunk(const float (&a)[64], float i0, float i1, uint32_t addr) {
#pragma unroll
  for (int i = 8 * H; i < 8 * H + 8; i += 2)
    stmatrix4(addr ^ ((i & 7) << 4), pack_bf(a[4 * i] * i0, a[4 * i + 1] * i0), pack_bf(a[4 * i + 2] * i1, a[4 * i + 3] * i1),
              pack_bf(a[4 * i + 4] * i0, a[4 * i + 5] * i0), pack_bf(a[4 * i + 6] * i1, a[4 * i + 7] * i1));
}
__device__ __forceinline__ float inv_quad_sum(float l) {
  l += __shfl_xor_sync(0xffffffffu, l, 1);
  l += __shfl_xor_sync(0xffffffffu, l, 2);
  return rcp(l);
}

__device__ __forceinline__ void write_table(uint32_t table, bool ca, uint32_t t, const uint4& m0, const uint4& m1) {
  float c0 = untag_sum(m0.x, m1.x), c1 = untag_sum(m0.y, m1.y), c2 = untag_sum(m0.z, m1.z), c3 = untag_sum(m0.w, m1.w);
  if (ca) { c0 = 1.f + rbf(c0); c1 = 1.f + rbf(c1); c2 = 1.f + rbf(c2); c3 = 1.f + rbf(c3); }
  const uint32_t d = table + (t >> 2) * 64 + (t & 1) * 32 + (t & 2) * 2 + (ca ? 0 : 8);
  sts1(d, pack_bf(c0, c1));
  sts1(d + 16, pack_bf(c2, c3));
}

__device__ __forceinline__ void ln_scalars(float mean, float var, float& mb, float& sd) {
  mb = rbf(mean);
  float r; asm("sqrt.approx.ftz.f32 %0, %1;" : "=f"(r) : "f"(rbf(rbf(var) + 1e-5f)));
  sd = rbf(r);
}

__global__ void __cluster_dims__(2, 1, 1) __launch_bounds__(384, 1) fused_kernel(const __grid_constant__ Maps maps, const Ptrs P) {
  extern __shared__ __align__(1024) uint8_t smem_raw[];
  const uint32_t base = smem_u32(smem_raw);
  const int tid = threadIdx.x, lane = tid & 31;
  const int warp = __shfl_sync(0xffffffffu, tid >> 5, 0);
  int b = blockIdx.x;
  if (b < NMAIN) {
    const int p = b >> 1;
    const int grp = p < 4 ? 7 : (p < 36 ? (p + 2) & 7 : (p - 30) % 7), k = p < 4 ? 4 + p : (p < 36 ? (p - 4) >> 3 : 4 + (p - 36) / 7);
    b = grp << 4 | k << 1 | (b & 1);
  }
  PROF(31, tid == 0, 0);

  if (b >= NMAIN) {
    float* sc = reinterpret_cast<float*>(smem_raw);
    float* red = sc + DM;
    for (int k = tid; k < DM; k += 384) sc[k] = rbf(silu_f(__bfloat162float(P.c[k])));
    __syncthreads();
    if (tid < 256) {
      const int col = 2048 + (b - NMAIN) * 1024 + (tid & 127) * 8, r0 = (tid >> 7) * 512;
      float acc[8];
#pragma unroll
      for (int e = 0; e < 8; e++) acc[e] = 0.f;
#pragma unroll 1
      for (int r = r0; r < r0 + 512; r += HU) {
        uint4 w[HU];
#pragma unroll
        for (int u = 0; u < HU; u++) w[u] = ldg_stream4(P.w_mod + (size_t)(r + u) * NMOD + col);
#pragma unroll
        for (int u = 0; u < HU; u++) {
          float s = sc[r + u];
          acc[0] += s * bf_lo(w[u].x); acc[1] += s * bf_hi(w[u].x); acc[2] += s * bf_lo(w[u].y); acc[3] += s * bf_hi(w[u].y);
          acc[4] += s * bf_lo(w[u].z); acc[5] += s * bf_hi(w[u].z); acc[6] += s * bf_lo(w[u].w); acc[7] += s * bf_hi(w[u].w);
        }
      }
      if (tid >= 128) {
#pragma unroll
        for (int e = 0; e < 8; e++) red[(tid & 127) * 8 + e] = acc[e];
      }
      const uint32_t tag = ld_relaxed(&g_epoch) % 3 + 1;
      bar_sync(1, 256);
      if (tid < 128) {
        uint32_t o[8];
#pragma unroll
        for (int e = 0; e < 8; e++) o[e] = __float_as_uint(rbf(acc[e] + red[tid * 8 + e])) | tag;
        st_relaxed4(g_mod + col, o[0], o[1], o[2], o[3]);
        st_relaxed4(g_mod + col + 4, o[4], o[5], o[6], o[7]);
        const uint4 wr = ldg_nc4(P.w_r + tid * 8);
        const uint32_t wv[4] = {wr.x, wr.y, wr.z, wr.w};
        float dsum = 0.f;
#pragma unroll
        for (int e = 0; e < 8; e++) {
          const float m = bf_hi(o[e]);
          dsum += (b == NMAIN + 2 ? rbf(1.f + m) : m) * ((e & 1) ? bf_hi(wv[e >> 1]) : bf_lo(wv[e >> 1]));
        }
#pragma unroll
        for (int k = 16; k > 0; k >>= 1) dsum += __shfl_xor_sync(0xffffffffu, dsum, k);
        if (lane == 0) st_relaxed(g_mod + (b - NMAIN) * 4 + warp, tagf(dsum, tag));
      }
    }
    PROF(2, tid == 0, 1);
    return;
  }

  const int rank = b & 1;
  const int rb = ((b >> 4) << 1) | rank, cj = (b >> 1) & 7;
  const bool late = b & 4;
  const uint32_t bfull = base + OFF_BAR, bempty = bfull + NSLOT * 8;
  const uint32_t gfull = bempty + NSLOT * 8, gempty = gfull + 32;
  const uint32_t bar_ofull = gempty + 32;
  const uint32_t bar_ofree = bar_ofull + 32;
  const uint32_t bar_par = bar_ofree + 32;
  const uint32_t bar_mod = bar_par + 8;
  const uint32_t bar_pread = bar_mod + 8;
  const uint32_t bar_xres = bar_pread + 8;
  const uint32_t bar_ring = bar_xres + 8;
  const uint32_t bar_box = bar_ring + 24;
  const uint32_t bar_go = bar_box + 96;
  const uint32_t bar_go2 = bar_go + 16;
  const uint32_t bar_cnt = bar_go + 24;
  const uint32_t xfull = bar_go + 40, xempty = xfull + 32;
  const uint32_t bar_hw = xempty + 32, bar_hx = bar_hw + 8;
  const uint32_t bar_hpub = bar_hx + 16;
  const uint32_t bar_win = bar_hpub + 16;
  const uint32_t bar_rx = bar_win + 8;
  const uint32_t bar_sel = bar_rx + 8;
  const uint32_t bar_gate = bar_sel + 8;
  const uint32_t bar_rel = bar_gate + 8;
  const uint32_t bar_od = bar_rel + 8;
  const uint32_t bar_mod2 = bar_od + 8;
  const uint32_t bar_res = bar_go + 8;
  const uint32_t stage = base + OFF_STAGE, par = base + OFF_PAR;

  if (warp == 10 && elect_one()) prefetch_map(&maps.wm);
  if (warp == 8 && elect_one()) {
    for (int s = 0; s < NSLOT; s++) { mbar_init(bfull + s * 8, 1); mbar_init(bempty + s * 8, 16); }
    for (int s = 0; s < 4; s++) { mbar_init(gfull + s * 8, 1); mbar_init(gempty + s * 8, 16); mbar_init(xfull + s * 8, 1); mbar_init(xempty + s * 8, 8); mbar_init(bar_ofree + s * 8, 1); mbar_init(bar_ofull + s * 8, 128); }
    mbar_init(bar_par, 64); mbar_init(bar_mod, 256); mbar_init(bar_pread, 2); mbar_init(bar_xres, 1);
    mbar_init(bar_ring, 8); mbar_init(bar_ring + 8, 8); mbar_init(bar_ring + 16, 8);
    mbar_init(bar_go, 1); mbar_init(bar_go2, 1); mbar_init(bar_cnt, 1); mbar_init(bar_cnt + 8, 1); mbar_init(bar_hpub, 8); mbar_init(bar_hpub + 8, 8); mbar_init(bar_res, 1); mbar_init(bar_win, 1); mbar_init(bar_rx, 1); mbar_init(bar_sel, 64); mbar_init(bar_gate, 8); mbar_init(bar_rel, 8); mbar_init(bar_od, 1); mbar_init(bar_mod2, 64);
    for (int s = 0; s < 12; s++) mbar_init(bar_box + s * 8, 1);
    asm volatile("fence.mbarrier_init.release.cluster;" ::: "memory");
    prefetch_map(&maps.x); prefetch_map(&maps.wq); prefetch_map(&maps.k); prefetch_map(&maps.v);
  }
  if (warp == 9 && elect_one()) {
    mbar_init(bar_hw, 1); mbar_init(bar_hx, 1); mbar_init(bar_hx + 8, 1);
    asm volatile("fence.mbarrier_init.release.cluster;" ::: "memory");
    mbar_expect_tx(bar_hw, 32768);
    mbar_expect_tx(bar_hx, 16384);
    mbar_expect_tx(bar_hx + 8, 16384);
    const __nv_bfloat16* xs = P.x + (size_t)(rb * 128 + cj * 16) * DM;
    bulk_load(base + 2 * GST_BYTES, xs, 16384, bar_hx);
    if (!late) {
      tma2d(stage, &maps.wm, (b >> 1) * 32, rank * 512, bar_hw);
      tma2d(stage + 16384, &maps.wm, (b >> 1) * 32, rank * 512 + 256, bar_hw);
    }
    bulk_load(base + 3 * GST_BYTES, xs + 8 * DM, 16384, bar_hx + 8);
  }
  cluster_arrive();

  if (warp >= 8) {
    asm volatile("setmaxnreg.dec.sync.aligned.u32 40;");
    if (warp < 10) bar_arrive(1, 320);
    const uint32_t epoch = ld_relaxed(&g_epoch);
    cluster_wait();
    if (warp == 8) {
      const int kvrow = (cj >> 1) * SK + (SK - WIN);
      int wch = cj * 8 + rank * 2;
#pragma unroll 1
      for (int ps = 0; ps < 3; ps++) {
        const CUtensorMap* mw = ps == 2 ? &maps.wo : &maps.wq;
        const uint32_t xt = ps == 1 ? XT1 : XT2, wt = ps == 0 ? WT0 : (ps == 1 ? WT1 : WT2);
        const int nst = ps == 2 ? 32 : 16;
#pragma unroll 1
        for (int i = 0; i < nst; i++) {
          const uint32_t bf = gfull + (i & 3) * 8;
          const int kt = ps == 2 ? (((cj & 1) * 4 + ((i >> 1) & 3)) * 4 + (i >> 3)) * 2 + (i & 1) : (ps ? i : slice_of(i) + (b & 14)) & 15;
          const uint32_t wd = base + unit_of(wt, i & 3) + rank * UNIT, xd = base + unit_of(xt, i & 3);
          const uint8_t* xs = g_act + (uint32_t)(rb * 80 + (ps - 1) * 16 + kt) * UNIT;
          if (ps == 0 && i == HD) mbar_wait(bar_mod, 0);
          if (ps == 2 && (i & 7) == 0 && i != 8) mbar_wait(i ? bar_cnt + i - 16 : bar_ofree + 24, 0);
          if ((i & 7) == 0) fence_async();
          if (i == RES0) mbar_wait(bar_res, 0);
          mbar_wait(bf, ((i >> 2) & 1) ^ 1);
          if (elect_one()) {
            mbar_expect_tx(bf, ps ? GST_BYTES : 2 * UNIT);
            if (ps && i < 2) bulk_load_stream(xd, xs, UNIT, bf);
            mbar_arrive_pred(bar_go, i == GOST);
            mbar_arrive_pred(bar_go2, ps == 1 && i == PG0);
            mbar_arrive_pred(bar_od, ps && i == (ps == 1 ? ODS1 : ODS) + 1);
            if (i == RES0) mbar_expect_tx(bar_xres, 32768);
          }
          const int wk = (i == 31 ? kt ^ (rank * 32) : kt) * 64, wc = i == 31 ? cj * 2 : wch;
          const uint64_t xp = i == 31 ? l2_normal() : l2_stream();
          mbar_wait(ps && i < 4 ? bempty + i * 8 : gempty + (i & 3) * 8, ((i >> 2) & 1) ^ 1);
          if (elect_one()) {
            tma3d_mc<true>(wd, mw, 0, wk, wc, bf);
            if (ps && i > 2) bulk_load_stream(xd, xs, UNIT, bf, xp);
            if (i == RES0 || i == RES1) tma2d(base + OFF_RES + (i == RES1) * UNIT, &maps.x, cj * 128 + (i == RES1) * 64, rb * 128, bar_xres);
          }
          if (ps && i == 2) {
            mbar_wait(bar_ofree + (ps - 1) * 16, 0);
            if (elect_one()) bulk_load_stream(xd, xs, UNIT, bf);
          }
        }
        if (ps == 2) break;
        wch = ps ? ((wch >> 3) ^ rank) * 2 : wch + 4;
#pragma unroll 1
        for (int u = 0; u < 16; u++) {
          const bool isk = (u == 0) || ((u & 1) && u < 15), kept = (0x1680 >> u) & 1;
          const int blk = (0x472FAD84u >> (u * 2)) & 3;
          const uint32_t sl = base + unit_of(ps ? AT1 : AT0, u & 3) + rank * UNIT, bf = bfull + (u & 3) * 8;
          mbar_wait(bf, ((u >> 2) & 1) ^ 1);
          if (!kept && elect_one()) mbar_expect_tx(bf, SLOT_BYTES);
          mbar_wait(u < 4 ? gempty + ((u + 1) >> 1) * 8 : bempty + (u & 3) * 8, ((u >> 2) & 1) ^ 1);
          if (elect_one()) {
            if (kept) mbar_arrive(bf);
            else if (ps && (blk >= 2 || u > 8)) tma3d_mc<true>(sl, isk ? &maps.k : &maps.v, 0, kvrow + blk * 128, rank, bf);
            else tma3d_mc<false>(sl, isk ? &maps.k : &maps.v, 0, kvrow + blk * 128, rank, bf);
          }
        }
      }
      if (elect_one()) mbar_expect_tx(bar_rx, UNIT);
      mbar_wait(bar_rel, 0);
      if (elect_one()) {
        bulk_load_stream(base + UNIT, g_act + (uint32_t)(rb * 80 + 16 + 63 - (cj & 1) * 32) * UNIT, UNIT, bar_rx);
      }
      if (b < NFFN) {
#pragma unroll 1
        for (int u = 0; u < 12; u++) {
          const uint32_t dst = base + unit_of(u < 4 ? FT_G : (u < 8 ? FT_U : FT_D), u & 3);
          if (elect_one()) mbar_expect_tx(bar_box + u * 8, UNIT);
          if (u == 0 || u == 2 || u == 8) mbar_wait(bar_ring + (u == 8 ? 16 : u * 4), 0);
          const int fp = u < 8 ? FPACE0 : FPACE;
          if (u >= fp) mbar_wait(bar_box + (u - fp) * 8, 0);
          if (elect_one()) {
            if (u < 8) tma2d(dst, u < 4 ? &maps.wg : &maps.wu, b * 32, (u & 3) * 256, bar_box + u * 8);
            else tma3d(dst, &maps.wd, 0, b * 32, (u - 8) * 4, bar_box + u * 8);
          }
        }
      }
    } else if (warp == 9) {
      const uint32_t target = 8 * (epoch + 1);
      uint32_t hmask = 0;
#pragma unroll 1
      for (int i = 0; i < 16; i++) {
        if (i == HDX) mbar_wait(bar_mod, 0);
        const int kt = (2 * cj + slice_of(i)) & 15;
        const uint32_t need = i == 15 ? 0xffffu : 1u << kt;
        if (i >= NRS && (hmask & need) != need) {
          uint32_t n = 0;
          do { hmask = __ballot_sync(0xffffffffu, ld_acquire(&g_cnt_h[rb * 32 + (lane & 15)]) == epoch + 1); watchdog(n); } while ((hmask & need) != need);
          PROF(1, lane == 0 && i == NRS, 26);
          fence_async();
        }
        mbar_wait(xempty + (i & 3) * 8, ((i >> 2) & 1) ^ 1);
        if (elect_one()) {
          mbar_expect_tx(xfull + (i & 3) * 8, UNIT);
          if (i < NRS) tma2d(base + (i & 3) * GST_BYTES, &maps.x, kt * 64, rb * 128, xfull + (i & 3) * 8);
          else bulk_load_stream(base + (i & 3) * GST_BYTES, g_act + (uint32_t)(rb * 80 + kt) * UNIT, UNIT, xfull + (i & 3) * 8);
        }
      }
      prefetch_map(&maps.wo);
#pragma unroll 1
      for (int t = 0; t < 4; t++) {
        if (t & 1) mbar_wait(bar_od, t >> 1);
        const int ops = OPS >> (t & 1);
#pragma unroll 1
        for (int p = 0; p < 32768; p += ops) {
          const uint32_t w = p >> 14, c = (p >> 13) & 1, off = w * 8192 + (p & 8191);
          mbar_wait(bar_ofull + (t & 1) * 16 + w * 8, t >> 1);
          if (elect_one()) {
            bulk_store(g_act + (uint32_t)(rb * 80 + 16 + (cj * 4 + t) * 2 + c) * UNIT + off, base + unit_of(QT, 2 * t + c) + off, ops);
            asm volatile("cp.async.bulk.commit_group;" ::: "memory");
            asm volatile("cp.async.bulk.wait_group.read 0;" ::: "memory");
          }
        }
        if (elect_one()) {
          mbar_arrive(t < 3 ? bar_ofree + t * 8 : bar_res);
          asm volatile("cp.async.bulk.wait_group 0;" ::: "memory");
          fence_async();
          red_release(&g_cnt_o[((rb * 4 + t) * 2 + (cj >> 2)) * 32], 2);
        }
        if (t) {
          wait_counter(&g_cnt_o[(rb * 8 + 2 * t + (cj & 1)) * 32], target);
          if (t & 1) wait_counter(&g_cnt_o[(rb * 8 + (t == 1 ? cj & 1 : 7 - (cj & 1))) * 32], target);
          if (elect_one()) mbar_arrive(t == 1 ? bar_ofree + 24 : bar_cnt + t * 8 - 16);
        }
      }
      PROF(2, lane == 0, 27);
      const uint32_t tag = epoch % 3 + 1;
      const uint32_t* inbox = g_cand + (b >> 4) % CR * 512 + (lane & 15) * CS;
      mbar_wait(bar_ring + 16, 0);
      uint32_t c0 = ld_relaxed(inbox), n = 0;
#define CAND_STEP(cv)                                                                                        \
      {                                                                                                      \
        const bool valid = (cv & 3u) == tag, all = __all_sync(0xffffffffu, valid);                           \
        const uint32_t best = __reduce_max_sync(0xffffffffu, valid ? cv : 0u);                               \
        const uint32_t blk = __ffs(__ballot_sync(0xffffffffu, cv == best)) - 1;                              \
        if (best) sts2(par + PAR_CONST + 56, best, (blk << 7 | (~best >> 2 & 127)) | (all ? 0x1800 : 0x800)); \
        if (all) break;                                                                                      \
        cv = ld_relaxed(inbox);                                                                              \
      }
      while (true) { CAND_STEP(c0) watchdog(n); }
    } else {
      const int t2 = tid - 320;
      if (late && warp == 10) {
        mbar_wait(bar_hx, 0);
        if (elect_one()) {
          tma2d(stage, &maps.wm, (b >> 1) * 32, rank * 512, bar_hw);
          tma2d(stage + 16384, &maps.wm, (b >> 1) * 32, rank * 512 + 256, bar_hw);
        }
      }
      {
        const uint32_t tag = epoch % 3 + 1;
        mbar_wait(bar_hx + 8, 0);
        mbar_wait(bar_hw, 0);
        __nanosleep(late ? OSL2 : OSL);
        {
          const uint32_t t7 = (warp & 1) * 64 + (lane >> 4) * 32 + 16 + (lane & 15);
          const uint32_t* pm = g_modp + ((cj * 128 + t7 * 4) & (DM - 1));
          uint4 m0, m1, m2, m3;
          uint32_t n = 0;
          do {
            m0 = ld_relaxed4(pm); m1 = ld_relaxed4(pm + 2 * DM); m2 = ld_relaxed4(pm + DM); m3 = ld_relaxed4(pm + 3 * DM);
            watchdog(n);
          } while (!__all_sync(0xffffffffu, tag_ok(m0, tag) && tag_ok(m1, tag) && tag_ok(m2, tag) && tag_ok(m3, tag)));
          write_table(par, false, t7, m0, m1);
          write_table(par, true, t7, m2, m3);
          mbar_arrive(bar_mod2);
        }
      }
      mbar_wait(bar_hpub + (warp & 1) * 8, 0);
      PROF(1, t2 == 0, 24);
#pragma unroll 1
      for (int c = 0; c < 8; c++) {
        const uint32_t off = (warp & 1) * UNIT + c * 2048 + lane * 16;
        uint8_t* dst = g_act + (uint32_t)(rb * 80 + cj * 2) * UNIT + off;
        const uint4 v0 = lds4(stage + off), v1 = lds4(stage + off + 512), v2 = lds4(stage + off + 1024), v3 = lds4(stage + off + 1536);
        stg4(dst, v0); stg4(dst + 512, v1); stg4(dst + 1024, v2); stg4(dst + 1536, v3);
      }
      __syncwarp();
      PROF(1, t2 == 0, 15);
      if (lane == 0) {
        mbar_arrive(bar_pread);
        red_release(&g_cnt_h[rb * 32 + cj * 2 + (warp & 1)], 1);
        PROF(1, t2 == 0, 25);
        prefetch_map(&maps.wg); prefetch_map(&maps.wu); prefetch_map(&maps.wd); prefetch_map(&maps.out);
      }
      __syncwarp();
      if (b < NFFN) {
        mbar_wait(bar_go2, 0);
        const __nv_bfloat16* pg = ((b & 1) ? P.w_up : P.w_gate) + (b >> 1) * 64 + (size_t)t2 * FF;
        const __nv_bfloat16* pd = P.w_down + (size_t)b * 32768 + t2 * 64;
        PROF(2, t2 == 0, 13);
#pragma unroll 1
        for (int i = 0; i < WN; i += WB) {
          uint32_t v[WB];
#pragma unroll
          for (int u = 0; u < WB; u++) {
            const int k = i + u;
            asm volatile("ld.global.cg.L2::128B.u32 %0, [%1];" : "=r"(v[u]) : "l"(k < 16 ? pg + (size_t)k * 64 * FF : pd + (k - 16) * 4096));
          }
#pragma unroll
          for (int u = 1; u < WB; u++) v[0] ^= v[u];
          sts1(par + PAR_SINK + t2 * 4, v[0]);
        }
        PROF(2, t2 == 0, 14);
      }
      const uint32_t tag = epoch % 3 + 1;
      mbar_wait(bar_go, 0);
      bar_sync(4, 64);
      if (warp == 10) {
        const uint32_t* src = g_mod + 2 * DM + cj * 128 + lane * 4;
        const uint2 wr = *reinterpret_cast<const uint2*>(P.w_r + cj * 128 + lane * 4);
        uint4 vga, vsb, vcb, vgb;
        uint32_t n = 0;
        do {
          vga = ld_relaxed4(src); vsb = ld_relaxed4(src + DM); vcb = ld_relaxed4(src + 2 * DM); vgb = ld_relaxed4(src + 3 * DM);
          watchdog(n);
        } while (!__all_sync(0xffffffffu, tag_ok(vga, tag) && tag_ok(vsb, tag) && tag_ok(vcb, tag) && tag_ok(vgb, tag)));
        const float c0 = rbf(1.f + bf_hi(vcb.x)), c1 = rbf(1.f + bf_hi(vcb.y)), c2 = rbf(1.f + bf_hi(vcb.z)), c3 = rbf(1.f + bf_hi(vcb.w));
        const float a0 = c0 * bf_lo(wr.x), a1 = c1 * bf_hi(wr.x), a2 = c2 * bf_lo(wr.y), a3 = c3 * bf_hi(wr.y);
        const uint32_t h0 = pack_bf(a0, a1), h1 = pack_bf(a2, a3);
        const uint32_t t1 = par + PAR_T1 + (lane >> 2) * 64 + (lane & 1) * 32 + (lane & 2) * 2;
        sts1(t1, h0); sts1(t1 + 8, pack_bf(a0 - bf_lo(h0), a1 - bf_hi(h0)));
        sts1(t1 + 16, h1); sts1(t1 + 24, pack_bf(a2 - bf_lo(h1), a3 - bf_hi(h1)));
        const uint32_t tg = par + PAR_SINK + (lane >> 3) * 64 + (lane & 1) * 32 + (lane & 6) * 2;
        sts1(tg, __byte_perm(vga.x, vga.y, 0x7632)); sts1(tg + 16, __byte_perm(vga.z, vga.w, 0x7632));
        sts4(par + PAR_T2 + lane * 32, make_uint4(pack_bf(c0, c1), __byte_perm(vsb.x, vsb.y, 0x7632), __byte_perm(vgb.x, vgb.y, 0x7632), __byte_perm(vga.x, vga.y, 0x7632)));
        sts4(par + PAR_T2 + lane * 32 + 16, make_uint4(pack_bf(c2, c3), __byte_perm(vsb.z, vsb.w, 0x7632), __byte_perm(vgb.z, vgb.w, 0x7632), __byte_perm(vga.z, vga.w, 0x7632)));
      } else {
        const uint4 g = poll4((lane & 8) ? g_mod + 8 - (lane & 1) * 4 : g_mod + 5 * DM + (b >> 4) * 128 + (lane & 7) * 16 + (b & 12), tag);
        sts1(par + PAR_CONST + 60, 0);
        if (lane < 8) sts1(par + PAR_CONST + 16 + lane * 4, (b & 2) ? ((b & 1) ? g.w : g.z) : ((b & 1) ? g.y : g.x));
        else if (lane < 10) sts2(par + PAR_CONST + (lane - 8) * 8, __float_as_uint(untag_sum(g.x, g.y) + untag_sum(g.z, g.w)), epoch);
      }
      __syncwarp();
#pragma unroll 1
      for (int q = 0; q < 32; q++) {
        st_b128(g_xch + ((size_t)b * 8 * 256 + q * 64 + t2) * 4, (epoch & 1) << 16, 0, 0, 0);
        __nanosleep(RSL);
      }
      for (int q = 0; q < 2; q++) st_relaxed4(g_stats + (((rb * 8 + q * 4 + (t2 >> 4)) * 8 + cj) * 16 + (t2 & 15)) * 4, 0, 0, 0, 0);
      if (b < NFFN)
        for (int q = 0; q < 2; q++) st_relaxed4(ypart_slot(b, q * 64 + t2), 0, 0, 0, 0);
      st_relaxed4(g_row + rb * 2 * DM + (t2 >> 5) * DM + cj * 128 + (t2 & 31) * 4, 0, 0, 0, 0);
      __threadfence();
      mbar_arrive(bar_par);
      mbar_wait(bar_gate, 0);
      uint32_t have = 0, n = 0;
      while (true) {
        const uint32_t st = lds1(par + PAR_CONST + 60) >> 7;
        if ((st & 31) != have) {
          const uint32_t* hsrc = g_row + (st & 15) * 2 * DM + t2 * 4;
          uint4 hv[4];
          bool ok = true;
#pragma unroll
          for (int i = 0; i < 4; i++) hv[i] = ld_pairs(hsrc + i * 256);
#pragma unroll
          for (int i = 0; i < 4; i++) {
            sts2(base + ((FT_G >> i * 4) & 15) * UNIT + (warp & 1) * 8192 + 256 + lane * 8, hv[i].x, hv[i].z);
            ok = ok && hv[i].y == tag && hv[i].w == tag;
          }
          have = __all_sync(0xffffffffu, ok) ? st & 31 : 0;
        }
        if ((st ^ have) == 32) break;
        watchdog(n);
      }
      mbar_arrive(bar_sel);
    }
    __syncwarp();
    cluster_arrive();
    {
      const uint32_t tag = epoch % 3 + 1, t3 = tid - 256;
      mbar_wait(bar_win, 0);
      uint2 win = lds2(par + PAR_CONST + 56);
      win.y &= 0x7ff;
      const uint32_t* fsrc = g_row + (win.y >> 7) * 2 * DM + (b >> 4) * 128 + (t3 & 7) * 16 + (b & 6) * 2 + ((b >> 2) & 2);
      const uint32_t* ysrc = ypart_slot(min(t3, NFFN - 1), b);
      uint2 fh = ld_pair(fsrc), fx = ld_pair(fsrc + DM);
      uint4 ya = ld_b128(ysrc);
      const float rwin = __uint_as_float(((int)win.x < 0 ? win.x & 0x7fffffffu : ~win.x) & ~0x1ffu);
      const float rs = rbf(rcp(1.f + __expf(-rbf(rwin))));
      uint32_t n = 0;
      while (__any_sync(0xffffffffu, fh.y != tag || fx.y != tag)) { fh = ld_pair(fsrc); fx = ld_pair(fsrc + DM); watchdog(n); }
      while (true) {
        const bool miss = ((ya.x & 1) | (ya.y & 1) << 1) != tag;
        if (!__any_sync(0xffffffffu, miss)) break;
        if (miss) ya = ld_b128(ysrc);
        watchdog(n);
      }
      PROF(8, t3 == 0, 5);
      float y[8] = {bf_lo(ya.x & ~1u), bf_hi(ya.x), bf_lo(ya.y & ~1u), bf_hi(ya.y), bf_lo(ya.z), bf_hi(ya.z), bf_lo(ya.w), bf_hi(ya.w)};
#pragma unroll
      for (int h = 4; h > 0; h >>= 1) {
        const bool up = lane & (h * 2);
#pragma unroll
        for (int e = 0; e < h; e++) y[e] = (up ? y[e + h] : y[e]) + __shfl_xor_sync(0xffffffffu, up ? y[e] : y[e + h], h * 2);
      }
      y[0] += __shfl_xor_sync(0xffffffffu, y[0], 1);
      if (!(lane & 1)) sts1(par + PAR_RED + 64 + t3 * 2, __float_as_uint(y[0]));
      bar_sync(4, 128);
      if (t3 < 8) {
        float y0 = 0.f;
#pragma unroll
        for (int w7 = 0; w7 < 7; w7++) y0 += __uint_as_float(lds1(par + PAR_RED + 64 + w7 * 32 + t3 * 4));
        const uint32_t gv = lds1(par + PAR_CONST + 16 + t3 * 4);
        const uint32_t upd = hmul2(pack_bf(y0, y0), pack_bf(rs, rs));
        const uint32_t r = hadd2(fx.x, hmul2(__byte_perm(gv, gv, 0x3232), hadd2(fh.x, upd)));
        reinterpret_cast<uint16_t*>(P.out)[(size_t)win.y * DM + (b >> 4) * 128 + t3 * 16 + (b & 15)] = (b & 1) ? r >> 16 : r;
        if (b == 0 && t3 == 0) st_relaxed(&g_epoch, epoch + 1);
      }
      PROF(31, t3 == 0, 36);
    }
    cluster_wait();
  } else {
    const int wg = warp >> 2;

    uint32_t tag;
    {
      uint32_t* const pmod = g_modp + rank * 2 * DM + (b >> 1) * 32 + lane;
      uint32_t* const pln = g_ln1 + (rb * 128 + cj * 16 + warp) * 4;
      uint32_t sc[8];
#pragma unroll
      for (int k = 0; k < 8; k++) sc[k] = ldg_nc1(P.c + rank * 512 + warp * 64 + k * 8 + (lane & 3) * 2);
      const uint32_t epoch = ld_relaxed(&g_epoch);
      if (warp == 0) st_relaxed(pmod, 0);
      if (lane == 0) { st_b128(pln, 0, 0, 0, 0); st_b128(pln + 32, 0, 0, 0, 0); }
      asm volatile("setmaxnreg.inc.sync.aligned.u32 232;");
      bar_sync(1, 320);
#pragma unroll
      for (int k = 0; k < 8; k++) sc[k] = pack_bf(silu_f(bf_lo(sc[k])), silu_f(bf_hi(sc[k])));
      keep(sc);
      tag = epoch % 3 + 1;
#pragma unroll
      for (int part = 0; part < 4; part++) {
        if (!(part & 1)) {
          const uint32_t xa = base + (2 + part / 2) * GST_BYTES + warp * 2048 + lane * 16;
          mbar_wait(bar_hx + part * 4, 0);
          float s0 = 0.f, s1 = 0.f, q0 = 0.f, q1 = 0.f;
#pragma unroll
          for (int q = 0; q < 4; q++) {
            const uint4 xv = lds4(xa + q * 512);
            const uint32_t u[4] = {xv.x, xv.y, xv.z, xv.w};
#pragma unroll
            for (int e = 0; e < 4; e++) { const float lo = bf_lo(u[e]), hi = bf_hi(u[e]); s0 += lo; s1 += hi; q0 += lo * lo; q1 += hi * hi; }
          }
          s0 += s1; q0 += q1;
#pragma unroll
          for (int o = 16; o > 0; o >>= 1) { s0 += __shfl_xor_sync(0xffffffffu, s0, o); q0 += __shfl_xor_sync(0xffffffffu, q0, o); }
          const float mean = s0 * (1.f / DM);
          float mb, sd;
          ln_scalars(mean, fmaxf(q0 * (1.f / DM) - mean * mean, 0.f), mb, sd);
          uint32_t ih, il;
          split_inv(sd, ih, il);
          if (lane == 0) st_b128(pln + part * 16, pack_bf(mb, mb), ih, il, tag);
          PROF(1, tid == 0 && part == 2, 4);
        } else if (late == (part == 3)) {
          const uint32_t fr = (lane & 7) + (lane >> 4) * 8, tq = lane & 3;
          const uint32_t wa = stage + warp * 4096 + fr * 64 + ((((lane >> 3) & 1) ^ ((fr >> 1) & 3)) << 4);
          float d0[4] = {0.f, 0.f, 0.f, 0.f}, d1[4] = {0.f, 0.f, 0.f, 0.f};
          mbar_wait(bar_hw, 0);
#pragma unroll
          for (int ks = 0; ks < 4; ks++) {
            uint32_t w[8];
            ldmatrix4t(wa + ks * 1024, w[0], w[1], w[2], w[3]);
            ldmatrix4t((wa ^ 32) + ks * 1024, w[4], w[5], w[6], w[7]);
            mma16816(d0, w[0], w[1], w[2], w[3], sc[2 * ks], sc[2 * ks + 1]);
            mma16816(d1, w[4], w[5], w[6], w[7], sc[2 * ks], sc[2 * ks + 1]);
          }
          sts1(base + 2 * GST_BYTES + warp * 2048 + (tq * 8 + (lane >> 2)) * 4, __float_as_uint((tq & 2) ? ((tq & 1) ? d1[2] : d1[0]) : ((tq & 1) ? d0[2] : d0[0])));
          bar_sync(1, 256);
          if (warp == 0) {
            float s = 0.f;
#pragma unroll
            for (int w8 = 0; w8 < 8; w8++) s += __uint_as_float(lds1(base + 2 * GST_BYTES + w8 * 2048 + lane * 4));
            st_relaxed(pmod, (__float_as_uint(s) & ~3u) | tag);
          }
          PROF(1, tid == 0, 3);
        }
      }
      cluster_wait();
      if (wg == 1) bar_arrive(2, 256);
    }

    float f0 = 0.f, f1 = 0.f;
    const uint32_t rempty = lane < 2 ? mapa(bempty, lane & 1) : 0;
    constexpr uint32_t GE = NSLOT * 8 + 32;
    float o[64], s[64];
#pragma unroll 1
    for (int ps = 0; ps < 3; ps++) {
      {
        const uint32_t xt = ps == 1 ? XT1 : XT2, wt = ps == 1 ? WT1 : WT2;
        const int nst = ps == 2 ? 28 : 14;
        if (ps == 0) {
          float ga[64], gb[64];
#pragma unroll
          for (int i = 0; i < 64; i++) { ga[i] = 0.f; gb[i] = 0.f; }
          uint32_t a[2][16];
          const uint32_t l = fresh_lane();
          uint32_t fa[4];
#pragma unroll
          for (int kk = 0; kk < 4; kk++) fa[kk] = (base + wg * 8192 + frag_offset(warp)) ^ (kk * 32);
          const uint32_t mt = par + (l & 3) * 16;
          auto fetch = [&](int i, uint32_t (&f)[16], uint32_t z) {
            mbar_wait(xfull + (i & 3) * 8, i >> 2);
#pragma unroll
            for (int kk = 0; kk < 4; kk++) ldmatrix4(fa[kk] + (i & 3) * GST_BYTES + z, f[4 * kk], f[4 * kk + 1], f[4 * kk + 2], f[4 * kk + 3]);
          };
          const bool oddw = warp & 2;
          uint4 r0, r1;
          {
            const uint32_t t7 = (warp & 1) * 64 + (l >> 4) * 32 + (l & 15);
            const uint32_t* pm = g_modp + wg * DM + ((cj * 128 + t7 * 4) & (DM - 1));
            const uint32_t* pr = g_ln1 + (rb * 128 + warp * 16 + (l >> 2)) * 4;
            uint4 m0 = make_uint4(tag, tag, tag, tag), m1 = m0;
            if (!oddw) { m0 = ld_relaxed4(pm); m1 = ld_relaxed4(pm + 2 * DM); }
            r0 = ld_b128(pr); r1 = ld_b128(pr + 32);
            fetch(0, a[0], 0); fetch(1, a[1], 0);
            uint32_t n = 0;
            bool written = false;
#pragma unroll 1
            while (true) {
              uint32_t miss;
              asm volatile("{ .reg .pred p0, p1, p2, p3; .reg .b32 t, u;\n"
                           "lop3.b32 t, %1, %2, %19, 0x7e; lop3.b32 u, %3, %4, %19, 0x7e; or.b32 t, t, u; and.b32 t, t, 3; setp.ne.u32 p0, t, 0;\n"
                           "lop3.b32 t, %5, %6, %19, 0x7e; lop3.b32 u, %7, %8, %19, 0x7e; or.b32 t, t, u; and.b32 t, t, 3; setp.ne.u32 p1, t, 0;\n"
                           "setp.ne.u32 p2, %12, %19; setp.ne.u32 p3, %16, %19;\n"
                           "@p0 ld.relaxed.gpu.global.v4.u32 {%1, %2, %3, %4}, [%17];\n"
                           "@p1 ld.relaxed.gpu.global.v4.u32 {%5, %6, %7, %8}, [%17 + 8192];\n"
                           "@p2 ld.relaxed.gpu.global.v4.u32 {%9, %10, %11, %12}, [%18];\n"
                           "@p3 ld.relaxed.gpu.global.v4.u32 {%13, %14, %15, %16}, [%18 + 128];\n"
                           "or.pred p0, p0, p1; or.pred p2, p2, p3; vote.sync.any.pred p0, p0, 0xffffffff; vote.sync.any.pred p2, p2, 0xffffffff;\n"
                           "selp.u32 t, 1, 0, p0; selp.u32 u, 2, 0, p2; or.b32 %0, t, u; }"
                           : "=r"(miss), "+r"(m0.x), "+r"(m0.y), "+r"(m0.z), "+r"(m0.w), "+r"(m1.x), "+r"(m1.y), "+r"(m1.z), "+r"(m1.w),
                             "+r"(r0.x), "+r"(r0.y), "+r"(r0.z), "+r"(r0.w), "+r"(r1.x), "+r"(r1.y), "+r"(r1.z), "+r"(r1.w)
                           : "l"(pm), "l"(pr), "r"(tag) : "memory");
              if (!(miss & 1) && !written) {
                written = true;
                if (!oddw) write_table(par, wg, t7, m0, m1);
                mbar_arrive(bar_mod);
              }
              if (!miss) break;
              watchdog(n);
            }
          }
          const uint32_t zero = r0.w ^ tag;
          auto normalize = [&](uint32_t (&f)[16]) {
#pragma unroll
            for (int k = 0; k < 16; k += 2) { f[k] = ln_norm(f[k], r0.x, r0.y, r0.z); f[k + 1] = ln_norm(f[k + 1], r1.x, r1.y, r1.z); }
          };
          auto modulate = [&](int i, uint32_t (&f)[16]) {
#pragma unroll
            for (int kk = 0; kk < 4; kk++) {
              const uint4 m = lds4(mt + slice_of(i) * 256 + kk * 64);
              f[4 * kk] = hfma2(f[4 * kk], m.x, m.z); f[4 * kk + 1] = hfma2(f[4 * kk + 1], m.x, m.z);
              f[4 * kk + 2] = hfma2(f[4 * kk + 2], m.y, m.w); f[4 * kk + 3] = hfma2(f[4 * kk + 3], m.y, m.w);
            }
            keep(f);
            mbar_arrive_pred(xempty + (i & 3) * 8, l == 0);
          };
          auto publish = [&](int u, uint32_t (&f)[16]) {
#pragma unroll
            for (int kk = 0; kk < 4; kk++) stmatrix4(fa[kk] + OFF_STAGE + u * UNIT, f[4 * kk], f[4 * kk + 1], f[4 * kk + 2], f[4 * kk + 3]);
            __syncwarp();
            mbar_arrive_pred(bar_hpub + u * 8, l == 0);
          };
          auto multiply = [&](int i, uint32_t (&f)[16]) {
            mbar_wait(gfull + (i & 3) * 8, i >> 2);
            const uint64_t db = make_desc(base + (i & 3) * GST_BYTES + UNIT, 8192, 1024);
            wg_fence();
#pragma unroll
            for (int kk = 0; kk < 4; kk++) mma256_rs(ga, gb, f[4 * kk], f[4 * kk + 1], f[4 * kk + 2], f[4 * kk + 3], db + kk * 128);
            wg_commit();
          };
          auto next = [&](int i, uint32_t (&f)[16]) {
            wg_wait<1>();
            mbar_arrive_cl(rempty, GE + ((i + 2) & 3) * 8);
            uint32_t z = zero;
#pragma unroll
            for (int k = 0; k < 16; k += 2) asm volatile("lop3.b32 %0, %1, %2, %0, 0xA8;" : "+r"(z) : "r"(f[k]), "r"(f[k + 1]));
            fetch(i, f, z);
            normalize(f);
            if (i == 2) { keep(f); mbar_wait(bar_mod2, 0); }
            modulate(i, f); multiply(i, f);
          };
          normalize(a[0]); normalize(a[1]);
          keep(a[0]); keep(a[1]);
          mbar_wait(bar_mod, 0);
          PROF(1, tid == 0, 2);
          modulate(0, a[0]); multiply(0, a[0]); publish(0, a[0]);
          modulate(1, a[1]); multiply(1, a[1]);
#pragma unroll 1
          for (int i = 2; i < NRS; i += 2) {
            next(i, a[0]);
            if (i == 2) publish(1, a[0]);
            next(i + 1, a[1]);
          }
          wg_wait<1>();
          mbar_arrive_cl(rempty, GE + ((NRS + 2) & 3) * 8);
#pragma unroll 1
          for (int i = NRS; i < 14; i++) {
            mbar_wait(xfull + (i & 3) * 8, (i >> 2) & 1);
            mbar_wait(gfull + (i & 3) * 8, (i >> 2) & 1);
            const uint32_t xa = base + (i & 3) * GST_BYTES;
            const uint64_t da = make_desc(xa + wg * 8192, 16, 1024), db = make_desc(xa + UNIT, 8192, 1024);
            if (i == 13) bar_sync(2 + wg, 256);
            wg_fence();
#pragma unroll
            for (int kk = 0; kk < 4; kk++) mma256_ss(ga, gb, da + kk * 2, db + kk * 128, 1);
            wg_commit();
            if (i == 13) bar_arrive(3 - wg, 256);
            wg_wait<1>();
            uint32_t z = zero;
#pragma unroll
            for (int k = 0; k < 16; k += 2) asm volatile("lop3.b32 %0, %1, %2, %0, 0xA8;" : "+r"(z) : "r"(a[1][k]), "r"(a[1][k + 1]));
            mbar_arrive_cl(rempty, GE + ((i + 3) & 3) * 8 + z);
            mbar_arrive_pred(xempty + ((i + 3) & 3) * 8, l == 0 && i != NRS);
          }
          mbar_wait(xfull + 16, 1);
          wg_wait<0>();
          keep(ga); keep(gb);
#pragma unroll
          for (int i = 0; i < 64; i++) {
            asm volatile("mov.b32 %0, %1;" : "=f"(s[i]) : "f"(ga[i]));
            asm volatile("mov.b32 %0, %1;" : "=f"(o[i]) : "f"(gb[i]));
          }
        } else {
          float ga[64], gb[64];
#pragma unroll
          for (int i = 0; i < 64; i++) {
            asm volatile("mov.b32 %0, %1;" : "=f"(ga[i]) : "f"(s[i]));
            asm volatile("mov.b32 %0, %1;" : "=f"(gb[i]) : "f"(o[i]));
          }
#pragma unroll 1
          for (int i = 0; i < nst; i++) {
            mbar_wait(gfull + (i & 3) * 8, (i >> 2) & 1);
            const uint64_t da = make_desc(base + unit_of(xt, i & 3) + wg * 8192, 16, 1024), db = make_desc(base + unit_of(wt, i & 3), 8192, 1024);
            if (i == nst - 1) bar_sync(2 + wg, 256);
            wg_fence();
#pragma unroll
            for (int kk = 0; kk < 4; kk++) mma256_ss(ga, gb, da + kk * 2, db + kk * 128, kk ? 1 : i);
            wg_commit();
            if (i == nst - 1) bar_arrive(3 - wg, 256);
            wg_wait<1>();
            mbar_arrive_cl(rempty, GE + ((i + 3) & 3) * 8, i != 0);
            PROF(4, tid == 0 && (i & 3) == 0, 40 + (ps - 1) * 4 + i / 4);
          }
          wg_wait<0>();
          keep(ga); keep(gb);
#pragma unroll
          for (int i = 0; i < 64; i++) {
            asm volatile("mov.b32 %0, %1;" : "=f"(s[i]) : "f"(ga[i]));
            asm volatile("mov.b32 %0, %1;" : "=f"(o[i]) : "f"(gb[i]));
          }
        }
        mbar_arrive_cl(rempty, GE + (ps == 2 ? 24 : 8));
        if (ps == 2) break;
      }
      const uint32_t qw = base + wg * 8192, qt = QT >> (16 * ps), at = ps ? AT1 : AT0;
      {
        const uint32_t wt = ps ? WT1 : WT0;
        const uint64_t da0 = make_desc(qw + unit_of(qt, 2), 16, 1024), da1 = make_desc(qw + unit_of(qt, 3), 16, 1024);
        const uint64_t db0 = make_desc(base + unit_of(wt, 2), 8192, 1024), db1 = make_desc(base + unit_of(wt, 3), 8192, 1024);
        mbar_wait(gfull + 16, 1);
        bar_sync(2 + wg, 256);
        wg_fence();
#pragma unroll
        for (int kk = 0; kk < 4; kk++) mma_ss<1>(s, da0 + kk * 2, db0 + kk * 128, 1);
        wg_commit();
        mbar_wait(xfull + 24, 1);
        mbar_wait(gfull + 24, 1);
        wg_fence();
#pragma unroll
        for (int kk = 0; kk < 4; kk++) mma_ss<1>(s, da1 + kk * 2, db1 + kk * 128, 1);
        wg_commit();
        bar_arrive(3 - wg, 256);
        mbar_wait(ps == 0 ? bar_pread : bar_ofree + 8, 0);
        wg_wait<0>();
        keep(s);
        PROF(2, tid == 0, 8 + ps * 8);
        uint32_t q[32];
        pack_p(s, q);
#pragma unroll
        for (int i = 0; i < 4; i++) stmatrix4((qw + unit_of(qt, 0) + frag_offset(warp)) ^ (i << 5), q[4 * i], q[4 * i + 1], q[4 * i + 2], q[4 * i + 3]);
        keep(q);
        bar_sync(2 + wg, 256);
        wg_fence();
#pragma unroll
        for (int kk = 0; kk < 8; kk++) mma_ss<1>(o, (kk < 4 ? da0 : da1) + (kk & 3) * 2, (kk < 4 ? db0 : db1) + UNIT / 16 + (kk & 3) * 128, 1);
        wg_commit();
        mbar_wait(bfull, 0);
        wg_fence();
        const uint64_t dk = make_desc(base + unit_of(at, 0), 16, 1024);
#pragma unroll
        for (int kk = 0; kk < 8; kk++) mma_rs<0>(s, q[4 * kk], q[4 * kk + 1], q[4 * kk + 2], q[4 * kk + 3], dk + (kk >> 2) * 1024 + (kk & 3) * 2, kk != 0);
        wg_commit();
        bar_arrive(3 - wg, 256);
#pragma unroll
        for (int i = 4; i < 8; i++) stmatrix4((qw + unit_of(qt, 1) + frag_offset(warp)) ^ ((i & 3) << 5), q[4 * i], q[4 * i + 1], q[4 * i + 2], q[4 * i + 3]);
        wg_wait<1>();
        keep(o);
        mbar_arrive_cl(rempty, GE + 16);
        mbar_arrive_cl(rempty, GE + 24);
        store_chunk<0>(o, qw + unit_of(qt, 2) + frag_offset(warp));
        store_chunk<1>(o, qw + unit_of(qt, 3) + frag_offset(warp));
        wg_wait<0>();
        keep(s);
        mbar_arrive_cl(rempty, 0);
      }
      PROF(4, tid == 0 && ps == 1, 61);
      float l0 = 0.f, l1 = 0.f;
      auto step = [&](auto odd_c, const int j, uint32_t (&pw)[32], uint32_t (&pr)[32]) {
        constexpr bool ODD = decltype(odd_c)::value;
        const bool first = !ODD && (j & 2) == 0, last = ODD && j == 7;
        const uint32_t ph = (j >> 1) & 1;
        float i0, i1, a0, a1;
        const bool so = !ODD && j == 4;
        if (so) { i0 = inv_quad_sum(l0); i1 = inv_quad_sum(l1); l0 = 0.f; l1 = 0.f; }
        bool redo = !ODD && (j | ps) == 0;
        while (true) {
          if (redo) {
            float m0 = fmaxf(s[0], s[1]), m1 = fmaxf(s[2], s[3]);
#pragma unroll
            for (int i = 1; i < 16; i++) { m0 = fmaxf(m0, fmaxf(s[4 * i], s[4 * i + 1])); m1 = fmaxf(m1, fmaxf(s[4 * i + 2], s[4 * i + 3])); }
            m0 = fmaxf(m0, __shfl_xor_sync(0xffffffffu, m0, 1)); m1 = fmaxf(m1, __shfl_xor_sync(0xffffffffu, m1, 1));
            m0 = fmaxf(m0, __shfl_xor_sync(0xffffffffu, m0, 2)); m1 = fmaxf(m1, __shfl_xor_sync(0xffffffffu, m1, 2));
            m0 *= SCL2; m1 *= SCL2;
            if (!first) {
              m0 = fmaxf(m0, f0); m1 = fmaxf(m1, f1);
              const float c0 = ex2(f0 - m0), c1 = ex2(f1 - m1);
              l0 *= c0; l1 *= c1;
              wg_wait<0>();
              keep(o);
#pragma unroll
              for (int i = 0; i < 16; i++) { o[4 * i] *= c0; o[4 * i + 1] *= c0; o[4 * i + 2] *= c1; o[4 * i + 3] *= c1; }
            }
            f0 = m0; f1 = m1;
          }
          float b0 = 0.f, b1 = 0.f;
          a0 = 0.f; a1 = 0.f;
#pragma unroll
          for (int i = 0; i < 16; i++) {
            const float e0 = ex2(fmaf(s[4 * i], SCL2, -f0)), e1 = ex2(fmaf(s[4 * i + 1], SCL2, -f0));
            const float e2 = ex2(fmaf(s[4 * i + 2], SCL2, -f1)), e3 = ex2(fmaf(s[4 * i + 3], SCL2, -f1));
            a0 += e0; b0 += e1; a1 += e2; b1 += e3;
            pw[2 * i] = pack_bf(e0, e1); pw[2 * i + 1] = pack_bf(e2, e3);
            if (i == VREL) {
#pragma unroll
              for (int k = 0; k < 2 * VREL + 2; k++) asm volatile("" : "+r"(pw[k])::"memory");
              mbar_wait(bar_mod, 0);
              wg_wait<0>();
              mbar_arrive_cl(rempty, ODD ? 16 : 0, !redo && (ODD || j));
#pragma unroll
              for (int k = 4 * VREL + 4; k < 64; k++) asm volatile("" : "+f"(s[k])::"memory");
            }
          }
          a0 += b0; a1 += b1;
          if (redo) break;
          redo = __any_sync(0xffffffffu, !(a0 + a1 < 0x1p90f) || (!ODD && fminf(a0, a1) < (first ? 0x1p-90f : 0.f)));
          if (!redo) break;
        }
        l0 += a0; l1 += a1;
        keep(pw);
        keep(o);
        if (so) store_chunk<0>(o, i0, i1, qw + unit_of(qt, 0) + frag_offset(warp));
        keep(o);
        if (j == (ODD ? 5 : 0)) { fence_async_smem(); if (ODD) mbar_arrive(bar_ofull + wg * 8); }
        mbar_wait(bfull + (ODD ? 24 : 8), ph);
        bar_sync(2 + wg, 256);
        if (!last) {
          const uint32_t qn = qt >> (j >= 3 ? 8 : 0);
          wg_fence();
          issue_qk(s, qw + unit_of(qn, 0), qw + unit_of(qn, 1), base + unit_of(at, ODD ? 3 : 1));
          wg_commit();
          mbar_wait(bfull + (ODD ? 0 : 16), ODD ? ph ^ 1 : ph);
        }
        if (so) { store_chunk<1>(o, i0, i1, qw + unit_of(qt, 1) + frag_offset(warp)); keep(o); }
        wg_fence();
        issue_pv(o, pw, base + unit_of(at, ODD ? (last ? 3 : 0) : 2), !first);
        wg_commit();
        bar_arrive(3 - wg, 256);
        wg_wait<1>();
        keep(s);
        mbar_arrive_cl(rempty, ODD ? 24 : 8, !last);
        PROF(4, tid == 0 && ps == 1, 51 + j);
      };
      uint32_t pa[32], pb[32];
#pragma unroll 1
      for (int j = 0; j < 8; j += 2) {
        step(std::false_type{}, j, pa, pb);
        step(std::true_type{}, j + 1, pb, pa);
      }
      {
        const float i0 = inv_quad_sum(l0), i1 = inv_quad_sum(l1);
        wg_wait<0>();
        keep(o);
        mbar_arrive_cl(rempty, 24);
        store_chunk<0>(o, i0, i1, qw + unit_of(qt, 2) + frag_offset(warp));
        store_chunk<1>(o, i0, i1, qw + unit_of(qt, 3) + frag_offset(warp));
        fence_async_smem();
        mbar_arrive(bar_ofull + 16 + wg * 8);
      }
      PROF(2, tid == 0, 10 + ps * 8);
    }

    const int ln = fresh_lane(), g = ln >> 2, tq = ln & 3, ct = warp * 32 + ln;
    const bool lane0 = ln == 0;
    const int lrow0 = warp * 16 + g;
    const uint32_t res = base + OFF_RES, trow = res + wg * 8192 + frag_offset(warp);
    uint32_t xr[32];
    uint4 sv[4], own;
    uint32_t* const sg = g_stats + (rb * 8 + warp) * 512 + g * 4;
    uint32_t* sp[4];
#pragma unroll
    for (int k = 0; k < 4; k++) sp[k] = sg + (tq & 1) * 32 + (((tq >> 1) ^ (cj >> 2)) * 4 + (k ^ (cj & 3))) * 64;
    {
      const uint64_t da = make_desc(base + wg * 8192, 16, 1024), db = make_desc(base, 8192, 1024);
      constexpr int U = UNIT / 16;
#define HALF_STAGE(acc, xu, wu) _Pragma("unroll") for (int kk = 0; kk < 4; kk++) mma_ss<1>(acc, da + (xu) * U + kk * 2, db + (wu) * U + kk * 128, 1)
      PROF(10, ct == PT, 19); STAMP(0);
      cluster_arrive();
      mbar_wait(gfull, 1);
      mbar_wait(gfull + 8, 1);
      bar_sync(2 + wg, 256);
      wg_fence();
      HALF_STAGE(o, 7, 1);
      HALF_STAGE(o, 8, 3);
      wg_commit();
      STAMP(16);
      mbar_wait(gfull + 16, 1);
      STAMP(17);
      wg_fence();
      HALF_STAGE(o, 6, 11);
      wg_commit();
      bar_arrive(3 - wg, 256);
      mbar_wait(bar_par, 0);
      uint32_t* xo = g_xch + ((size_t)b * 8 * 256 + ct) * 4;
      const uint32_t* xi = g_xch + ((size_t)(b ^ 2) * 8 * 256 + ct) * 4;
      const uint32_t par1 = (~lds1(par + PAR_CONST + 4) & 1) << 16;
      wg_wait<1>();
      mbar_arrive_pred(bar_rel, lane0);
      wg_wait<0>();
      keep(o);
      mbar_arrive_pred(bar_ring, lane0);
      PROF(8, ct == PT, 20); STAMP(1);
#define SEND(i) st_b128(xo + (i) * 1024, (pack_bf(o[8 * (i)], o[8 * (i) + 1]) & ~0x10000u) | par1, pack_bf(o[8 * (i) + 2], o[8 * (i) + 3]), \
                        pack_bf(o[8 * (i) + 4], o[8 * (i) + 5]), pack_bf(o[8 * (i) + 6], o[8 * (i) + 7]))
#pragma unroll
      for (int i = 0; i < NS1; i++) SEND(i);
      PROF(8, ct == PT, 21); STAMP(2);
      bar_sync(2 + wg, 256);
      wg_fence();
      HALF_STAGE(s, 7, 0);
      HALF_STAGE(s, 8, 2);
      HALF_STAGE(s, 6, 10);
      wg_commit();
      bar_arrive(3 - wg, 256);
      STAMP(18);
      mbar_wait(gfull + 24, 1);
#pragma unroll
      for (int i = NS1; i < 8; i++) SEND(i);
      uint4 v[8];
      STAMP(19);
      mbar_wait(bar_xres, 0);
      wg_wait<0>();
      mbar_arrive_pred(bar_ring + 8, lane0);
      bar_sync(2 + wg, 256);
      STAMP(20);
#pragma unroll
      for (int i = 0; i < LD2; i++) v[i] = ld_b128(xi + i * 1024);
      mbar_wait(bar_xres, 0);
      wg_fence();
      HALF_STAGE(s, 9, 4);
      wg_commit();
      mbar_wait(bar_rx, 0);
      wg_fence();
      HALF_STAGE(s, 1, 5);
      wg_commit();
      bar_arrive(3 - wg, 256);
      STAMP(21);
#pragma unroll
      for (int i = LD2; i < 8; i++) v[i] = ld_b128(xi + i * 1024);
      mbar_wait(bar_xres, 0);
      wg_wait<0>();
      keep(s);
      mbar_arrive_pred(bar_ring + 16, lane0);
      PROF(10, ct == PT, 23); STAMP(4);
#pragma unroll
      for (int i = 0; i < 16; i += 2) ldmatrix4((trow ^ ((i & 7) << 4)) + (i >> 3) * 16384, xr[2 * i], xr[2 * i + 1], xr[2 * i + 2], xr[2 * i + 3]);
      uint32_t ga[16];
      uint4 bw[8];
#pragma unroll
      for (int i = 0; i < 8; i++) {
        if (!(i & 1)) {
          const uint4 t = lds4(par + PAR_SINK + i * 32 + tq * 16);
          ga[2 * i] = t.x; ga[2 * i + 1] = t.y; ga[2 * i + 2] = t.z; ga[2 * i + 3] = t.w;
        }
        bw[i] = lds4(par + PAR_T1 + i * 64 + tq * 16);
        if (!(g & 1)) { bw[i].x = 0x3f803f80u; bw[i].y = 0x3f803f80u; }
      }
      uint32_t pk[32];
      pack_p(s, pk);
      const uint32_t par2 = (~lds1(par + PAR_CONST + 12) & 1) << 16;
      {
        uint32_t n = 0, miss;
        do {
          miss = 0;
#pragma unroll
          for (int i = 0; i < 8; i++) miss |= v[i].x ^ par2;
          miss = __any_sync(0xffffffffu, miss & 0x10000u);
          if (miss) {
#pragma unroll
            for (int i = 0; i < 8; i++)
              asm volatile("{ .reg .pred p; .reg .b32 t; xor.b32 t, %0, %5; and.b32 t, t, 0x10000; setp.ne.u32 p, t, 0;\n"
                           "@p ld.relaxed.gpu.global.v4.u32 {%0, %1, %2, %3}, [%4]; }"
                           : "+r"(v[i].x), "+r"(v[i].y), "+r"(v[i].z), "+r"(v[i].w) : "l"(xi + i * 1024), "r"(par1) : "memory");
          }
          watchdog(n);
        } while (miss);
      }
      PROF(8, ct == PT, 22); STAMP(3);
      float ds[4] = {0.f, 0.f, 0.f, 0.f}, dl[4] = {0.f, 0.f, 0.f, 0.f}, q0[4] = {0.f, 0.f, 0.f, 0.f}, q1[4] = {0.f, 0.f, 0.f, 0.f};
#pragma unroll
      for (int i = 0; i < 8; i++) {
        const uint32_t u0 = hfma2(ga[2 * i], hadd2(pk[4 * i], v[i].x & ~0x10000u), xr[4 * i]);
        const uint32_t u1 = hfma2(ga[2 * i], hadd2(pk[4 * i + 1], v[i].y), xr[4 * i + 1]);
        const uint32_t u2 = hfma2(ga[2 * i + 1], hadd2(pk[4 * i + 2], v[i].z), xr[4 * i + 2]);
        const uint32_t u3 = hfma2(ga[2 * i + 1], hadd2(pk[4 * i + 3], v[i].w), xr[4 * i + 3]);
        xr[4 * i] = u0; xr[4 * i + 1] = u1; xr[4 * i + 2] = u2; xr[4 * i + 3] = u3;
        mma16816(ds, u0, u1, u2, u3, bw[i].x, bw[i].y);
        mma16816(dl, u0, u1, u2, u3, bw[i].z, bw[i].w);
        mma16816(q0, u0, u1, u2, u3, u0, u2);
        mma16816(q1, u0, u1, u2, u3, u1, u3);
      }
      const float sqa = (g & 1) ? q0[1] : q0[0], sqb = (g & 1) ? q1[3] : q1[2], dta = ds[1] + dl[1], dtb = ds[3] + dl[3];
      if (tq == (g >> 1)) {
        st_b128(sg + cj * 64, __float_as_uint(ds[0]), __float_as_uint(sqa), __float_as_uint(dta), tag);
        st_b128(sg + cj * 64 + 32, __float_as_uint(ds[2]), __float_as_uint(sqb), __float_as_uint(dtb), tag);
      }
#pragma unroll
      for (int k = 0; k < 4; k++) sv[k] = ld_b128(sp[k]);
      mbar_wait(bar_xres, 0);
      const float sqc = __shfl_sync(0xffffffffu, sqa, g * 4 + (g >> 1)), sqd = __shfl_sync(0xffffffffu, sqb, g * 4 + (g >> 1));
      own = (tq & 1) ? make_uint4(__float_as_uint(ds[2]), __float_as_uint(sqd), __float_as_uint(dtb), tag)
                     : make_uint4(__float_as_uint(ds[0]), __float_as_uint(sqc), __float_as_uint(dta), tag);
    }
    PROF(8, ct == PT, 29); STAMP(5);
    uint32_t mm, ih, il;
    float rbest;
    uint32_t wf[128];
    const uint32_t frow = (ln & 7) + (ln >> 4) * 8;
    const uint32_t wfo = base + (warp & 1) * 8192 + frow * 64 + ((((ln >> 3) & 1) ^ ((frow >> 1) & 3)) << 4);
#define LOAD_WF(m) _Pragma("unroll") for (int f = 0; f < 16; f++) {                                                   \
      const int r = ((f >> 1) * 4 + (m) * 2 + (f & 1)) * 4;                                                           \
      ldmatrix4t(((wfo + unit_of((m) ? FT_U : FT_G, warp >> 1)) ^ ((f & 1) * 32)) + (f >> 1) * 1024, wf[r], wf[r + 1], wf[r + 2], wf[r + 3]); \
    }
    bool early;
    {
#pragma unroll
      for (int i = 0; i < 16; i += 2) stmatrix4((trow ^ ((i & 7) << 4)) + (i >> 3) * 16384, xr[2 * i], xr[2 * i + 1], xr[2 * i + 2], xr[2 * i + 3]);
      const uint4 cst = lds4(par + PAR_CONST);
      const float A1 = __uint_as_float(cst.x), A2 = __uint_as_float(cst.z);
      uint32_t n = 0;
      early = false;
#pragma unroll 1
      while (true) {
        if (!early && (b >= NFFN || __all_sync(0xffffffffu, mbar_test(bar_box + (warp >> 1) * 8, 0)))) {
          early = true;
          LOAD_WF(0);
          __syncwarp();
          mbar_arrive_pred(bar_gate, lane0);
        }
        uint32_t miss;
        asm volatile("{ .reg .pred p0, p1, p2, p3; .reg .b64 u, v; .reg .b128 w;\n"
                     "setp.ge.u32 p0, %22, 2; setp.ne.and.u32 p0, %4, %21, p0; setp.ne.u32 p1, %8, %21; setp.ne.u32 p2, %12, %21; setp.ne.u32 p3, %16, %21;\n"
                     "@p0 ld.relaxed.gpu.global.v4.u32 {%1, %2, %3, %4}, [%17];\n"
                     "@p1 ld.relaxed.gpu.global.v4.u32 {%5, %6, %7, %8}, [%18];\n"
                     "@p2 ld.relaxed.gpu.global.v4.u32 {%9, %10, %11, %12}, [%19];\n"
                     "@p3 ld.relaxed.gpu.global.v4.u32 {%13, %14, %15, %16}, [%20];\n"
                     "or.pred p0, p0, p1; or.pred p2, p2, p3; or.pred p0, p0, p2; vote.sync.any.pred p0, p0, 0xffffffff; selp.u32 %0, 1, 0, p0; }"
                     : "=r"(miss), "+r"(sv[0].x), "+r"(sv[0].y), "+r"(sv[0].z), "+r"(sv[0].w), "+r"(sv[1].x), "+r"(sv[1].y), "+r"(sv[1].z), "+r"(sv[1].w),
                       "+r"(sv[2].x), "+r"(sv[2].y), "+r"(sv[2].z), "+r"(sv[2].w), "+r"(sv[3].x), "+r"(sv[3].y), "+r"(sv[3].z), "+r"(sv[3].w)
                     : "l"(sp[0]), "l"(sp[1]), "l"(sp[2]), "l"(sp[3]), "r"(tag), "r"(tq) : "memory");
        if (!miss) break;
        watchdog(n);
      }
      const uint4 v0 = tq < 2 ? own : sv[0], v1 = sv[1], v2 = sv[2], v3 = sv[3];
      PROF(8, ct == PT, 30); STAMP(6);
      float su = (__uint_as_float(v0.x) + __uint_as_float(v1.x)) + (__uint_as_float(v2.x) + __uint_as_float(v3.x));
      float sq = (__uint_as_float(v0.y) + __uint_as_float(v1.y)) + (__uint_as_float(v2.y) + __uint_as_float(v3.y));
      float dt = (__uint_as_float(v0.z) + __uint_as_float(v1.z)) + (__uint_as_float(v2.z) + __uint_as_float(v3.z));
      su += __shfl_xor_sync(0xffffffffu, su, 2); sq += __shfl_xor_sync(0xffffffffu, sq, 2); dt += __shfl_xor_sync(0xffffffffu, dt, 2);
      const float m = su * (1.f / DM);
      float mb, sd;
      ln_scalars(m, fmaxf(sq * (1.f / DM) - m * m, 0.f), mb, sd);
      const float inv = rcp(sd);
      rbest = (dt - mb * A1) * inv + A2;
      mm = pack_bf(mb, mb);
      ih = pack_bf(inv, inv);
      const float lo = inv - bf_lo(ih);
      il = pack_bf(lo, lo);
    }
    int ibest;
    {
      const uint32_t bits = __float_as_uint(rbest);
      const uint32_t key = (((int)bits < 0 ? ~bits : bits | 0x80000000u) & ~0x1ffu) | ((127 - lrow0 - (tq & 1) * 8) << 2) | tag;
      sts1(par + PAR_RED + warp * 4, __reduce_max_sync(0xffffffffu, key));
      PROF(8, ct == PT, 38); STAMP(7);
      bar_sync(1, 256);
      const uint4 ka = lds4(par + PAR_RED), kb = lds4(par + PAR_RED + 16);
      const uint32_t k2 = max(max(max(ka.x, ka.y), max(ka.z, ka.w)), max(max(kb.x, kb.y), max(kb.z, kb.w)));
      if (ct < CR && cj == 0) st_relaxed(g_cand + ct * 512 + rb * CS, k2);
      ibest = 127 - ((k2 >> 2) & 127);
    }
    PROF(8, ct == PT, 39); STAMP(8);
    if ((ibest >> 4) == warp) {
      const int src = (ibest & 7) * 4 + ((ibest >> 3) & 1), ch = g * 2;
      const uint32_t cm = __shfl_sync(0xffffffffu, mm, src), ch_ = __shfl_sync(0xffffffffu, ih, src), cl = __shfl_sync(0xffffffffu, il, src);
      const uint32_t xa = res + (ch >> 3) * 16384 + ibest * 128 + (((ch & 7) ^ (ibest & 7)) << 4) + tq * 4;
      const uint32_t x0 = lds1(xa), x1 = lds1(xa ^ 16);
      const uint2 p0 = lds2(par + PAR_T2 + ch * 64 + tq * 16), p1 = lds2(par + PAR_T2 + ch * 64 + 64 + tq * 16);
      uint32_t* dst = g_row + rb * 2 * DM + cj * 128 + ln * 4;
      st_pairs(dst, ln_mod(x0, cm, ch_, cl, p0.x, p0.y), ln_mod(x1, cm, ch_, cl, p1.x, p1.y), tag);
      st_pairs(dst + DM, x0, x1, tag);
      __syncwarp();
    }
    PROF(8, ct == PT, 37); STAMP(9);
    uint32_t wd[64];
    const uint32_t wda = base + unit_of(FT_D, warp >> 1) + (warp & 1) * 8192 + frow * 128 + ((((ln >> 3) & 1) ^ (ln & 7)) << 4);
#define LOAD_WD(f) ldmatrix4t((wda ^ ((((f) >> 1) & 3) * 32)) + ((f) >> 3) * 4096 + ((f) & 1) * 2048, wd[4 * (f)], wd[4 * (f) + 1], wd[4 * (f) + 2], wd[4 * (f) + 3])
    if (!early) {
      if (b < NFFN) mbar_wait(bar_box + (warp >> 1) * 8, 0);
      LOAD_WF(0);
      __syncwarp();
      mbar_arrive_pred(bar_gate, lane0);
    }
    if (b < NFFN) {
      const uint32_t own = base + unit_of(FT_G, warp >> 1) + (warp & 1) * 8192;
      mbar_wait(bar_box + (4 + (warp >> 1)) * 8, 0);
      LOAD_WF(1);
      uint32_t* const ydst = ypart_slot(b, warp * 16 + (tq & 1) * 8 + g);
      PROF(8, ct == PT, 31); STAMP(10);
      bool wdok;
      {
        uint32_t n = 0;
        while (!(wdok = __all_sync(0xffffffffu, mbar_test(bar_box + (8 + (warp >> 1)) * 8, 0))) && !__all_sync(0xffffffffu, mbar_test(bar_sel, 0))) watchdog(n);
      }
      if (wdok) {
#pragma unroll
        for (int f = 0; f < 16; f++) LOAD_WD(f);
      }
      STAMP(11);
      mbar_wait(bar_sel, 0);
      PROF(8, ct == PT, 33); STAMP(12);
      float d[8][4];
#pragma unroll
      for (int i = 0; i < 4; i++) { d[i][0] = 0.f; d[i][1] = 0.f; d[i][2] = 0.f; d[i][3] = 0.f; }
#pragma unroll
      for (int ks = 0; ks < 8; ks++) {
        const uint2 hb = lds2(own + 256 + ks * 32 + tq * 8);
#pragma unroll
        for (int mt = 0; mt < 4; mt++) {
          const int r = ks * 16 + mt * 4;
          mma16816(d[mt], wf[r], wf[r + 1], wf[r + 2], wf[r + 3], hb.x, hb.y);
        }
      }
      sts2(own + (tq * 8 + g) * 8, __float_as_uint((tq & 2) ? ((tq & 1) ? d[1][2] : d[1][0]) : ((tq & 1) ? d[0][2] : d[0][0])),
           __float_as_uint((tq & 2) ? ((tq & 1) ? d[3][2] : d[3][0]) : ((tq & 1) ? d[2][2] : d[2][0])));
      bar_sync(1, 256);
      uint32_t ab[4];
      {
        float G = 0.f, U = 0.f;
        uint2 pv[8];
#pragma unroll
        for (int w8 = 0; w8 < 8; w8++) pv[w8] = lds2(base + ln * 8 + ((FT_G >> (w8 >> 1) * 4) & 15) * UNIT + (w8 & 1) * 8192);
#pragma unroll
        for (int w8 = 0; w8 < 8; w8 += 2) {
          G += __uint_as_float(pv[w8].x) + __uint_as_float(pv[w8 + 1].x);
          U += __uint_as_float(pv[w8].y) + __uint_as_float(pv[w8 + 1].y);
        }
        const float act = rbf(silu_f(rbf(G))) * rbf(U);
        const uint32_t pk = pack_bf(act, __shfl_down_sync(0xffffffffu, act, 1));
#pragma unroll
        for (int i = 0; i < 4; i++) ab[i] = __shfl_sync(0xffffffffu, pk, i * 8 + tq * 2);
      }
      if (!wdok) {
        mbar_wait(bar_box + (8 + (warp >> 1)) * 8, 0);
#pragma unroll
        for (int f = 0; f < 16; f++) LOAD_WD(f);
      }
      PROF(8, ct == PT, 34); STAMP(13);
#pragma unroll
      for (int mt = 0; mt < 8; mt++) {
        d[mt][0] = 0.f; d[mt][1] = 0.f; d[mt][2] = 0.f; d[mt][3] = 0.f;
        mma16816(d[mt], wd[mt * 8], wd[mt * 8 + 1], wd[mt * 8 + 2], wd[mt * 8 + 3], ab[0], ab[1]);
        mma16816(d[mt], wd[mt * 8 + 4], wd[mt * 8 + 5], wd[mt * 8 + 6], wd[mt * 8 + 7], ab[2], ab[3]);
      }
      uint32_t yw[4];
#pragma unroll
      for (int i = 0; i < 4; i++) yw[i] = (tq & 1) ? pack_bf(d[2 * i][2], d[2 * i + 1][2]) : pack_bf(d[2 * i][0], d[2 * i + 1][0]);
      if (tq < 2) st_b128(ydst, (yw[0] & ~1u) | (tag & 1), (yw[1] & ~1u) | (tag >> 1), yw[2], yw[3]);
      PROF(8, ct == PT, 35); STAMP(14);
    }
    mbar_wait(bar_sel, 0);
    mbar_arrive_pred(bar_win, ct == 0);
    const int iwin = lds1(par + PAR_CONST + 60) & 0x7ff;
    const bool cand = (iwin >> 4) == rb * 8 + warp;
    {
      const uint32_t mm0 = __shfl_sync(0xffffffffu, mm, ln & ~1), mm1 = __shfl_sync(0xffffffffu, mm, ln | 1);
      const uint32_t ih0 = __shfl_sync(0xffffffffu, ih, ln & ~1), ih1 = __shfl_sync(0xffffffffu, ih, ln | 1);
      const uint32_t il0 = __shfl_sync(0xffffffffu, il, ln & ~1), il1 = __shfl_sync(0xffffffffu, il, ln | 1);
#pragma unroll 1
      for (int hf = 0; hf < 2; hf++) {
        uint32_t x[16];
#pragma unroll
        for (int i = 0; i < 8; i += 2) ldmatrix4((trow ^ (i << 4)) + hf * 16384, x[2 * i], x[2 * i + 1], x[2 * i + 2], x[2 * i + 3]);
#pragma unroll
        for (int i = 0; i < 8; i++) {
          const uint4 pv = lds4(par + PAR_T2 + (hf * 8 + i) * 64 + tq * 16);
          x[2 * i] = hfma2(hfma2(ln_norm(x[2 * i], mm0, ih0, il0), pv.x, pv.y), pv.z, x[2 * i]);
          x[2 * i + 1] = hfma2(hfma2(ln_norm(x[2 * i + 1], mm1, ih1, il1), pv.x, pv.y), pv.z, x[2 * i + 1]);
        }
#pragma unroll
        for (int i = 0; i < 8; i += 2) stmatrix4((trow ^ (i << 4)) + hf * 16384, x[2 * i], x[2 * i + 1], x[2 * i + 2], x[2 * i + 3]);
        if (!cand) fence_async_smem();
        __syncwarp();
        if (!cand && elect_one()) {
          tma2d_store(&maps.out, res + hf * 16384 + warp * 2048, cj * 128 + hf * 64, rb * 128 + warp * 16);
          asm volatile("cp.async.bulk.commit_group;" ::: "memory");
        }
      }
    }
    if (cand) {
      const int wrow0 = warp * 16;
#pragma unroll 2
      for (int p = 0; p < 8; p++) {
        const int row = 2 * p + (ln >> 4), ch = ln & 15;
        const uint4 v = lds4(res + (ch >> 3) * 16384 + (wrow0 + row) * 128 + (((ch & 7) ^ (row & 7)) << 4));
        if (rb * 128 + wrow0 + row != iwin) *reinterpret_cast<uint4*>(P.out + (size_t)(rb * 128 + wrow0 + row) * DM + cj * 128 + ch * 8) = v;
      }
    }
    asm volatile("cp.async.bulk.wait_group.read 0;" ::: "memory");
    PROF(8, ct == PT, 11); STAMP(15);
    cluster_wait();
  }
}

typedef CUresult (*EncodeFn)(CUtensorMap*, CUtensorMapDataType, cuuint32_t, void*, const cuuint64_t*, const cuuint64_t*,
                             const cuuint32_t*, const cuuint32_t*, CUtensorMapInterleave, CUtensorMapSwizzle,
                             CUtensorMapL2promotion, CUtensorMapFloatOOBfill);

void map2d(EncodeFn enc, CUtensorMap* m, const void* p, uint64_t rows, uint64_t cols, uint32_t brows) {
  cuuint64_t dims[2] = {cols, rows}, strides[1] = {cols * 2};
  cuuint32_t box[2] = {64, brows}, es[2] = {1, 1};
  enc(m, CU_TENSOR_MAP_DATA_TYPE_BFLOAT16, 2, const_cast<void*>(p), dims, strides, box, es, CU_TENSOR_MAP_INTERLEAVE_NONE,
      CU_TENSOR_MAP_SWIZZLE_128B, CU_TENSOR_MAP_L2_PROMOTION_L2_256B, CU_TENSOR_MAP_FLOAT_OOB_FILL_NONE);
}
void map2d_narrow(EncodeFn enc, CUtensorMap* m, const void* p, uint64_t rows, uint64_t cols, uint32_t brows) {
  cuuint64_t dims[2] = {cols, rows}, strides[1] = {cols * 2};
  cuuint32_t box[2] = {32, brows}, es[2] = {1, 1};
  enc(m, CU_TENSOR_MAP_DATA_TYPE_BFLOAT16, 2, const_cast<void*>(p), dims, strides, box, es, CU_TENSOR_MAP_INTERLEAVE_NONE,
      CU_TENSOR_MAP_SWIZZLE_64B, CU_TENSOR_MAP_L2_PROMOTION_L2_64B, CU_TENSOR_MAP_FLOAT_OOB_FILL_NONE);
}
void map3d(EncodeFn enc, CUtensorMap* m, const void* p, uint64_t rows, uint64_t cols, uint32_t brows, uint32_t nch) {
  cuuint64_t dims[3] = {64, rows, cols / 64}, strides[2] = {cols * 2, 128};
  cuuint32_t box[3] = {64, brows, nch}, es[3] = {1, 1, 1};
  enc(m, CU_TENSOR_MAP_DATA_TYPE_BFLOAT16, 3, const_cast<void*>(p), dims, strides, box, es, CU_TENSOR_MAP_INTERLEAVE_NONE,
      CU_TENSOR_MAP_SWIZZLE_128B, CU_TENSOR_MAP_L2_PROMOTION_L2_256B, CU_TENSOR_MAP_FLOAT_OOB_FILL_NONE);
}

}

extern "C" void kernel_launch(void* const* d_in, const int* in_sizes, int n_in, void* d_out, int out_size) {
  (void)in_sizes; (void)n_in; (void)out_size;
  static EncodeFn enc = nullptr;
  if (!enc) {
    void* fn = nullptr;
    cudaDriverEntryPointQueryResult st;
    cudaGetDriverEntryPoint("cuTensorMapEncodeTiled", &fn, cudaEnableDefault, &st);
    enc = (EncodeFn)fn;
    cudaFuncSetAttribute(fused_kernel, cudaFuncAttributeMaxDynamicSharedMemorySize, SMEM_BYTES);
  }
  Maps maps;
  map2d(enc, &maps.x, d_in[0], SEQ, DM, 128);
  map2d(enc, &maps.out, d_out, SEQ, DM, 16);
  map3d(enc, &maps.wq, d_in[3], DM, NQ, 64, 2);
  map3d(enc, &maps.k, d_in[1], 4 * SK, 128, 128, 1);
  map3d(enc, &maps.v, d_in[2], 4 * SK, 128, 128, 1);
  map3d(enc, &maps.wo, d_in[4], NQ, DM, 64, 2);
  map2d_narrow(enc, &maps.wg, d_in[7], DM, FF, 256);
  map2d_narrow(enc, &maps.wu, d_in[8], DM, FF, 256);
  map3d(enc, &maps.wd, d_in[9], FF, DM, 32, 4);
  map2d_narrow(enc, &maps.wm, d_in[11], DM, NMOD, 256);
  Ptrs p;
  p.x = (const __nv_bfloat16*)d_in[0];
  p.w_r = (const __nv_bfloat16*)d_in[6];
  p.w_gate = (const __nv_bfloat16*)d_in[7];
  p.w_up = (const __nv_bfloat16*)d_in[8];
  p.w_down = (const __nv_bfloat16*)d_in[9];
  p.c = (const __nv_bfloat16*)d_in[10];
  p.w_mod = (const __nv_bfloat16*)d_in[11];
  p.out = (__nv_bfloat16*)d_out;
  fused_kernel<<<NMAIN + NHELP, 384, SMEM_BYTES>>>(maps, p);
}
```

```cpp
#include <cuda_runtime.h>
#include <cuda_bf16.h>
#include <cuda.h>
#include <stdint.h>
#include <type_traits>

#define HD 2
#define HDX 2
#define NRS 8
#define OSL 900
#define OSL2 400
#define RSL 40
#define BIAS 96.f
#define PMX 16
#define VREL 5
#define OPS 8192
#define ODS1 5
#define ODS 7
#define PG0 15
#define WB 2
#define WN 20
#define HU 32
#define RES0 17
#define RES1 20
#define GOST 20
#define NS1 5
#define LD2 4
#define FPACE0 2
#define FPACE 3
#define CR 8
#define CS 8

namespace {

constexpr int SEQ = 2048, DM = 1024, NQ = 4096, SK = 2048, WIN = 512, FF = 3584, NMOD = 6144;
constexpr int NMAIN = 128, NHELP = 4, NFFN = 112;
constexpr int NSLOT = 4, SLOT_BYTES = 32768, UNIT = 16384, GST_BYTES = 3 * UNIT;
constexpr uint32_t XT1 = 0xDCBA, XT2 = 0x9687;
constexpr uint32_t WT0 = 0xA741, WT1 = 0x7420, WT2 = 0x4A20;
constexpr uint32_t AT0 = WT1, AT1 = WT2;
constexpr uint32_t QT = 0xDC9696DC;
constexpr int OFF_STAGE = 12 * UNIT;
constexpr uint32_t FT_G = 0x07B3, FT_U = 0xA628, FT_D = 0x5149;
constexpr int OFF_RES = 12 * UNIT;
constexpr int OFF_PAR = 14 * UNIT;
constexpr int OFF_BAR = OFF_PAR + 2528;
constexpr int SMEM_BYTES = OFF_BAR + 544;
static_assert(SMEM_BYTES <= 232448, "smem");

constexpr int PAR_T1 = 0;
constexpr int PAR_T2 = 512;
constexpr int PAR_CONST = 1536;
constexpr int PAR_RED = 1600;
constexpr int PAR_SINK = 2176;

struct Maps {
  CUtensorMap x, wq, k, v, wo, wg, wu, wd, wm, out;
};
struct Ptrs {
  const __nv_bfloat16 *x, *w_r, *c, *w_mod, *w_gate, *w_up, *w_down;
  __nv_bfloat16* out;
};

__device__ __align__(1024) uint8_t g_act[16 * 80 * UNIT];
__device__ __align__(128) uint32_t g_mod[NMOD];
__device__ __align__(128) uint32_t g_modp[2 * 2 * DM];
__device__ __align__(128) uint32_t g_ln1[SEQ * 4];
__device__ __align__(128) uint32_t g_cnt_h[16 * 32];
__device__ __align__(128) uint32_t g_cnt_o[128 * 32];
__device__ __align__(128) uint32_t g_xch[NMAIN * 8 * 256 * 4];
__device__ __align__(128) uint32_t g_stats[8 * SEQ * 4];
__device__ __align__(128) uint32_t g_cand[CR * 512];
__device__ __align__(128) uint32_t g_row[16 * 2 * DM];
__device__ __align__(128) uint32_t g_ypart[NMAIN * NFFN * 4];
__device__ __forceinline__ uint32_t* ypart_slot(int writer, int reader) { return g_ypart + (writer * NMAIN + reader) * 4; }
__device__ uint32_t g_epoch;

__device__ __forceinline__ uint32_t fresh_lane() { uint32_t l; asm volatile("mov.u32 %0, %%laneid;" : "=r"(l)); return l; }
__device__ __forceinline__ uint32_t frag_offset(int warp) {
  const uint32_t l = fresh_lane();
  return ((warp & 3) * 16 + (l & 15)) * 128 + (((l >> 4) ^ (l & 7)) << 4);
}
__device__ __forceinline__ bool elect_one() {
  uint32_t p;
  asm volatile("{ .reg .pred q; elect.sync _|q, 0xffffffff; selp.u32 %0, 1, 0, q; }" : "=r"(p));
  return p;
}
__device__ __forceinline__ uint32_t smem_u32(const void* p) { return (uint32_t)__cvta_generic_to_shared(p); }
__device__ __forceinline__ void mbar_init(uint32_t bar, uint32_t cnt) {
  asm volatile("mbarrier.init.shared::cta.b64 [%0], %1;" ::"r"(bar), "r"(cnt) : "memory");
}
__device__ __forceinline__ void mbar_expect_tx(uint32_t bar, uint32_t bytes) {
  asm volatile("mbarrier.arrive.expect_tx.shared::cta.b64 _, [%0], %1;" ::"r"(bar), "r"(bytes) : "memory");
}
__device__ __forceinline__ void mbar_arrive(uint32_t bar) {
  asm volatile("mbarrier.arrive.shared::cta.b64 _, [%0];" ::"r"(bar) : "memory");
}
__device__ __forceinline__ void mbar_arrive_pred(uint32_t bar, bool p) {
  asm volatile("{ .reg .pred p; setp.ne.b32 p, %1, 0; @p mbarrier.arrive.shared::cta.b64 _, [%0]; }" ::"r"(bar), "r"((int)p) : "memory");
}
__device__ __forceinline__ void mbar_arrive_cl(uint32_t bar, uint32_t off, bool p = true) {
  asm volatile("{ .reg .pred p, q; .reg .b32 a; setp.ne.b32 q, %2, 0; setp.ne.and.b32 p, %0, 0, q; add.u32 a, %0, %1; @p mbarrier.arrive.shared::cluster.b64 _, [a]; }"
               ::"r"(bar), "r"(off), "r"((int)p) : "memory");
}
__device__ __forceinline__ uint32_t mapa(uint32_t addr, uint32_t cta) {
  uint32_t r; asm("mapa.shared::cluster.u32 %0, %1, %2;" : "=r"(r) : "r"(addr), "r"(cta)); return r;
}
__device__ __forceinline__ void cluster_arrive() { asm volatile("barrier.cluster.arrive.relaxed.aligned;" ::: "memory"); }
__device__ __forceinline__ void cluster_wait() { asm volatile("barrier.cluster.wait.aligned;" ::: "memory"); }
__device__ __forceinline__ void watchdog(uint32_t& n) {
}
__device__ __forceinline__ void mbar_wait(uint32_t bar, uint32_t parity) {
  asm volatile("{\n.reg .pred p;\nWAIT_%=:\nmbarrier.try_wait.parity.shared::cta.b64 p, [%0], %1;\n@!p bra WAIT_%=;\n}" ::"r"(bar), "r"(parity) : "memory");
}
__device__ __forceinline__ bool mbar_test(uint32_t bar, uint32_t parity) {
  uint32_t ok;
  asm volatile("{\n.reg .pred p;\nmbarrier.test_wait.parity.shared::cta.b64 p, [%1], %2;\nselp.u32 %0, 1, 0, p;\n}" : "=r"(ok) : "r"(bar), "r"(parity) : "memory");
  return ok;
}
__device__ __forceinline__ uint64_t l2_stream() {
  uint64_t f; asm("createpolicy.fractional.L2::evict_first.b64 %0, 1.0;" : "=l"(f)); return f;
}
__device__ __forceinline__ uint64_t l2_normal() {
  uint64_t f; asm("createpolicy.fractional.L2::evict_normal.b64 %0, 1.0;" : "=l"(f)); return f;
}
__device__ __forceinline__ void tma2d(uint32_t dst, const CUtensorMap* m, int c0, int c1, uint32_t bar) {
  asm volatile("cp.async.bulk.tensor.2d.shared::cluster.global.mbarrier::complete_tx::bytes.L2::cache_hint [%0], [%1, {%3, %4}], [%2], %5;"
               ::"r"(dst), "l"(m), "r"(bar), "r"(c0), "r"(c1), "l"(l2_stream()) : "memory");
}
__device__ __forceinline__ void bulk_load(uint32_t dst, const void* src, uint32_t bytes, uint32_t bar) {
  asm volatile("cp.async.bulk.shared::cluster.global.mbarrier::complete_tx::bytes [%0], [%1], %2, [%3];" ::"r"(dst), "l"(src), "r"(bytes), "r"(bar) : "memory");
}
__device__ __forceinline__ void bulk_load_stream(uint32_t dst, const void* src, uint32_t bytes, uint32_t bar, uint64_t pol = l2_stream()) {
  asm volatile("cp.async.bulk.shared::cluster.global.mbarrier::complete_tx::bytes.L2::cache_hint [%0], [%1], %2, [%3], %4;"
               ::"r"(dst), "l"(src), "r"(bytes), "r"(bar), "l"(pol) : "memory");
}
__device__ __forceinline__ void tma2d_store(const CUtensorMap* m, uint32_t src, int c0, int c1) {
  asm volatile("cp.async.bulk.tensor.2d.global.shared::cta.bulk_group [%0, {%2, %3}], [%1];" ::"l"(m), "r"(src), "r"(c0), "r"(c1) : "memory");
}
__device__ __forceinline__ void bulk_store(void* dst, uint32_t src, uint32_t bytes) {
  asm volatile("cp.async.bulk.global.shared::cta.bulk_group [%0], [%1], %2;" ::"l"(dst), "r"(src), "r"(bytes) : "memory");
}
__device__ __forceinline__ int slice_of(int i) { return i + ((i & 7) == 1) - ((i & 7) == 2); }
__device__ __forceinline__ uint32_t unit_of(uint32_t table, uint32_t i) { return ((table >> (i * 4)) & 15) * UNIT; }
__device__ __forceinline__ void tma3d(uint32_t dst, const CUtensorMap* m, int c0, int c1, int c2, uint32_t bar) {
  asm volatile("cp.async.bulk.tensor.3d.shared::cluster.global.mbarrier::complete_tx::bytes.L2::cache_hint [%0], [%1, {%3, %4, %5}], [%2], %6;"
               ::"r"(dst), "l"(m), "r"(bar), "r"(c0), "r"(c1), "r"(c2), "l"(l2_stream()) : "memory");
}
template <bool STREAM>
__device__ __forceinline__ void tma3d_mc(uint32_t dst, const CUtensorMap* m, int c0, int c1, int c2, uint32_t bar) {
  if (STREAM)
    asm volatile("cp.async.bulk.tensor.3d.shared::cluster.global.mbarrier::complete_tx::bytes.multicast::cluster.L2::cache_hint [%0], [%1, {%3, %4, %5}], [%2], %6, %7;"
                 ::"r"(dst), "l"(m), "r"(bar), "r"(c0), "r"(c1), "r"(c2), "h"((uint16_t)3), "l"(l2_stream()) : "memory");
  else
    asm volatile("cp.async.bulk.tensor.3d.shared::cluster.global.mbarrier::complete_tx::bytes.multicast::cluster [%0], [%1, {%3, %4, %5}], [%2], %6;"
                 ::"r"(dst), "l"(m), "r"(bar), "r"(c0), "r"(c1), "r"(c2), "h"((uint16_t)3) : "memory");
}
__device__ __forceinline__ void prefetch_map(const CUtensorMap* m) {
  asm volatile("prefetch.tensormap [%0];" ::"l"(m) : "memory");
}
__device__ __forceinline__ void fence_async() { asm volatile("fence.proxy.async.global;" ::: "memory"); }
__device__ __forceinline__ void fence_async_smem() { asm volatile("fence.proxy.async.shared::cta;" ::: "memory"); }
__device__ __forceinline__ void bar_sync(int id, int n) { asm volatile("bar.sync %0, %1;" ::"r"(id), "r"(n) : "memory"); }
__device__ __forceinline__ void bar_arrive(int id, int n) { asm volatile("bar.arrive %0, %1;" ::"r"(id), "r"(n) : "memory"); }
__device__ __forceinline__ void wg_fence() { asm volatile("wgmma.fence.sync.aligned;" ::: "memory"); }
__device__ __forceinline__ void wg_commit() { asm volatile("wgmma.commit_group.sync.aligned;" ::: "memory"); }
template <int N> __device__ __forceinline__ void wg_wait() { asm volatile("wgmma.wait_group.sync.aligned %0;" ::"n"(N) : "memory"); }
__device__ __forceinline__ uint64_t make_desc(uint32_t addr, uint32_t lbo, uint32_t sbo) {
  return (uint64_t)((addr & 0x3FFFF) >> 4) | ((uint64_t)(lbo >> 4) << 16) | ((uint64_t)(sbo >> 4) << 32) | (1ull << 62);
}
__device__ __forceinline__ uint32_t ld_relaxed(const uint32_t* p) {
  uint32_t v; asm volatile("ld.relaxed.gpu.global.u32 %0, [%1];" : "=r"(v) : "l"(p) : "memory"); return v;
}
__device__ __forceinline__ uint32_t ld_acquire(const uint32_t* p) {
  uint32_t v; asm volatile("ld.acquire.gpu.global.u32 %0, [%1];" : "=r"(v) : "l"(p) : "memory"); return v;
}
__device__ __forceinline__ uint4 ld_relaxed4(const uint32_t* p) {
  uint4 v; asm volatile("ld.relaxed.gpu.global.v4.u32 {%0,%1,%2,%3}, [%4];" : "=r"(v.x), "=r"(v.y), "=r"(v.z), "=r"(v.w) : "l"(p) : "memory"); return v;
}
__device__ __forceinline__ void st_relaxed(uint32_t* p, uint32_t v) {
  asm volatile("st.relaxed.gpu.global.u32 [%0], %1;" ::"l"(p), "r"(v) : "memory");
}
__device__ __forceinline__ void st_relaxed4(uint32_t* p, uint32_t a, uint32_t b, uint32_t c, uint32_t d) {
  asm volatile("st.relaxed.gpu.global.v4.u32 [%0], {%1,%2,%3,%4};" ::"l"(p), "r"(a), "r"(b), "r"(c), "r"(d) : "memory");
}
__device__ __forceinline__ void st_b128(uint32_t* p, uint32_t a, uint32_t b, uint32_t c, uint32_t d) {
  asm volatile("{ .reg .b64 u, v; .reg .b128 w; mov.b64 u, {%1, %2}; mov.b64 v, {%3, %4}; mov.b128 w, {u, v}; st.relaxed.gpu.global.b128 [%0], w; }"
               ::"l"(p), "r"(a), "r"(b), "r"(c), "r"(d) : "memory");
}
__device__ __forceinline__ uint4 ld_b128(const uint32_t* p) {
  uint4 r;
  asm volatile("{ .reg .b64 u, v; .reg .b128 w; ld.relaxed.gpu.global.b128 w, [%4]; mov.b128 {u, v}, w; mov.b64 {%0, %1}, u; mov.b64 {%2, %3}, v; }"
               : "=r"(r.x), "=r"(r.y), "=r"(r.z), "=r"(r.w) : "l"(p) : "memory");
  return r;
}
__device__ __forceinline__ void st_pairs(uint32_t* p, uint32_t a, uint32_t b, uint32_t tag) {
  asm volatile("{ .reg .b64 u, v; mov.b64 u, {%1, %3}; mov.b64 v, {%2, %3}; st.relaxed.gpu.global.v2.b64 [%0], {u, v}; }"
               ::"l"(p), "r"(a), "r"(b), "r"(tag) : "memory");
}
__device__ __forceinline__ uint4 ld_pairs(const uint32_t* p) {
  uint4 v;
  asm volatile("{ .reg .b64 u, v; ld.relaxed.gpu.global.v2.b64 {u, v}, [%4]; mov.b64 {%0, %1}, u; mov.b64 {%2, %3}, v; }"
               : "=r"(v.x), "=r"(v.y), "=r"(v.z), "=r"(v.w) : "l"(p) : "memory");
  return v;
}
__device__ __forceinline__ uint2 ld_pair(const uint32_t* p) {
  uint2 v;
  asm volatile("{ .reg .b64 u; ld.relaxed.gpu.global.b64 u, [%2]; mov.b64 {%0, %1}, u; }" : "=r"(v.x), "=r"(v.y) : "l"(p) : "memory");
  return v;
}
__device__ __forceinline__ void red_release(uint32_t* p, uint32_t v) {
  asm volatile("red.release.gpu.global.add.u32 [%0], %1;" ::"l"(p), "r"(v) : "memory");
}
__device__ __forceinline__ uint32_t ldg_nc1(const void* p) {
  uint32_t v;
  asm volatile("ld.global.nc.u32 %0, [%1];" : "=r"(v) : "l"(p));
  return v;
}
__device__ __forceinline__ uint4 ldg_nc4(const void* p) {
  uint4 v; asm volatile("ld.global.nc.L1::no_allocate.v4.u32 {%0,%1,%2,%3}, [%4];" : "=r"(v.x), "=r"(v.y), "=r"(v.z), "=r"(v.w) : "l"(p)); return v;
}
__device__ __forceinline__ uint4 ldg_stream4(const void* p) {
  uint4 v;
  asm volatile("ld.global.nc.L1::no_allocate.L2::cache_hint.v4.u32 {%0,%1,%2,%3}, [%4], %5;" : "=r"(v.x), "=r"(v.y), "=r"(v.z), "=r"(v.w) : "l"(p), "l"(l2_stream()));
  return v;
}
__device__ __forceinline__ void stg4(void* p, uint4 v) {
  asm volatile("st.global.v4.u32 [%0], {%1,%2,%3,%4};" ::"l"(p), "r"(v.x), "r"(v.y), "r"(v.z), "r"(v.w) : "memory");
}
__device__ __forceinline__ void wait_counter(const uint32_t* p, uint32_t target) {
  uint32_t n = 0;
  while (__any_sync(0xffffffffu, (int)(ld_acquire(p) - target) < 0)) { watchdog(n); }
}
__device__ __forceinline__ uint32_t tagf(float v, uint32_t tag) { return (__float_as_uint(v) & ~3u) | tag; }
__device__ __forceinline__ bool tag_ok(uint4 v, uint32_t tag) { return (((v.x ^ tag) | (v.y ^ tag) | (v.z ^ tag) | (v.w ^ tag)) & 3u) == 0; }
__device__ __forceinline__ float untag_sum(uint32_t a, uint32_t b) { return __uint_as_float(a & ~3u) + __uint_as_float(b & ~3u); }
__device__ __forceinline__ uint4 poll4(const uint32_t* p, uint32_t tag) {
  uint4 v = ld_relaxed4(p);
  uint32_t n = 0;
  while (!__all_sync(0xffffffffu, tag_ok(v, tag))) { v = ld_relaxed4(p); watchdog(n); }
  return v;
}
__device__ __forceinline__ float bf_lo(uint32_t v) { return __uint_as_float(v << 16); }
__device__ __forceinline__ float bf_hi(uint32_t v) { return __uint_as_float(v & 0xffff0000u); }
__device__ __forceinline__ uint32_t pack_bf(float lo, float hi) {
  uint32_t r; asm("cvt.rn.bf16x2.f32 %0, %1, %2;" : "=r"(r) : "f"(hi), "f"(lo)); return r;
}
__device__ __forceinline__ float rbf(float v) { return __uint_as_float(pack_bf(0.f, v) & 0xffff0000u); }
__device__ __forceinline__ uint32_t hmul2(uint32_t a, uint32_t b) {
  uint32_t r; asm("mul.rn.bf16x2 %0, %1, %2;" : "=r"(r) : "r"(a), "r"(b)); return r;
}
__device__ __forceinline__ uint32_t hadd2(uint32_t a, uint32_t b) {
  uint32_t r; asm("add.rn.bf16x2 %0, %1, %2;" : "=r"(r) : "r"(a), "r"(b)); return r;
}
__device__ __forceinline__ uint32_t hsub2(uint32_t a, uint32_t b) {
  uint32_t r; asm("sub.rn.bf16x2 %0, %1, %2;" : "=r"(r) : "r"(a), "r"(b)); return r;
}
__device__ __forceinline__ float rcp(float x) { float r; asm("rcp.approx.ftz.f32 %0, %1;" : "=f"(r) : "f"(x)); return r; }
__device__ __forceinline__ float ex2(float x) { float r; asm("ex2.approx.ftz.f32 %0, %1;" : "=f"(r) : "f"(x)); return r; }
__device__ __forceinline__ void stmatrix4(uint32_t addr, uint32_t a, uint32_t b, uint32_t c, uint32_t d) {
  asm volatile("stmatrix.sync.aligned.m8n8.x4.shared.b16 [%0], {%1,%2,%3,%4};" ::"r"(addr), "r"(a), "r"(b), "r"(c), "r"(d) : "memory");
}
__device__ __forceinline__ void ldmatrix4(uint32_t addr, uint32_t& a, uint32_t& b, uint32_t& c, uint32_t& d) {
  asm volatile("ldmatrix.sync.aligned.m8n8.x4.shared.b16 {%0,%1,%2,%3}, [%4];" : "=r"(a), "=r"(b), "=r"(c), "=r"(d) : "r"(addr) : "memory");
}
__device__ __forceinline__ void ldmatrix4t(uint32_t addr, uint32_t& a, uint32_t& b, uint32_t& c, uint32_t& d) {
  asm volatile("ldmatrix.sync.aligned.m8n8.x4.trans.shared.b16 {%0,%1,%2,%3}, [%4];" : "=r"(a), "=r"(b), "=r"(c), "=r"(d) : "r"(addr) : "memory");
}
__device__ __forceinline__ void mma16816(float (&d)[4], uint32_t a0, uint32_t a1, uint32_t a2, uint32_t a3, uint32_t b0, uint32_t b1) {
  asm volatile("mma.sync.aligned.m16n8k16.row.col.f32.bf16.bf16.f32 {%0,%1,%2,%3}, {%4,%5,%6,%7}, {%8,%9}, {%0,%1,%2,%3};"
               : "+f"(d[0]), "+f"(d[1]), "+f"(d[2]), "+f"(d[3]) : "r"(a0), "r"(a1), "r"(a2), "r"(a3), "r"(b0), "r"(b1));
}
__device__ __forceinline__ void sts1(uint32_t a, uint32_t v) { asm volatile("st.shared.u32 [%0], %1;" ::"r"(a), "r"(v) : "memory"); }
__device__ __forceinline__ uint4 lds4(uint32_t a) {
  uint4 v; asm volatile("ld.shared.v4.u32 {%0,%1,%2,%3}, [%4];" : "=r"(v.x), "=r"(v.y), "=r"(v.z), "=r"(v.w) : "r"(a) : "memory"); return v;
}
__device__ __forceinline__ uint2 lds2(uint32_t a) {
  uint2 v; asm volatile("ld.shared.v2.u32 {%0,%1}, [%2];" : "=r"(v.x), "=r"(v.y) : "r"(a) : "memory"); return v;
}
__device__ __forceinline__ uint32_t lds1(uint32_t a) {
  uint32_t v; asm volatile("ld.shared.u32 %0, [%1];" : "=r"(v) : "r"(a) : "memory"); return v;
}
__device__ __forceinline__ void sts2(uint32_t a, uint32_t x, uint32_t y) { asm volatile("st.shared.v2.u32 [%0], {%1,%2};" ::"r"(a), "r"(x), "r"(y) : "memory"); }
__device__ __forceinline__ void sts4(uint32_t a, uint4 v) {
  asm volatile("st.shared.v4.u32 [%0], {%1,%2,%3,%4};" ::"r"(a), "r"(v.x), "r"(v.y), "r"(v.z), "r"(v.w) : "memory");
}
__device__ __forceinline__ float silu_f(float v) { return __fdividef(v, 1.f + __expf(-v)); }
__device__ __forceinline__ uint32_t hfma2(uint32_t a, uint32_t b, uint32_t c) {
  uint32_t r; asm("fma.rn.bf16x2 %0, %1, %2, %3;" : "=r"(r) : "r"(a), "r"(b), "r"(c)); return r;
}
__device__ __forceinline__ void split_inv(float sd, uint32_t& ih, uint32_t& il) {
  const float inv = rcp(sd);
  ih = pack_bf(inv, inv);
  const float lo = inv - bf_lo(ih);
  il = pack_bf(lo, lo);
}
__device__ __forceinline__ uint32_t ln_norm(uint32_t x, uint32_t mean2, uint32_t ih, uint32_t il) {
  const uint32_t d = hsub2(x, mean2);
  return hfma2(d, ih, hmul2(d, il));
}
__device__ __forceinline__ uint32_t ln_mod(uint32_t x, uint32_t mean2, uint32_t ih, uint32_t il, uint32_t c1, uint32_t sh) {
  return hadd2(hmul2(ln_norm(x, mean2, ih, il), c1), sh);
}

#define R8(a, i) "+f"(a[i]), "+f"(a[i + 1]), "+f"(a[i + 2]), "+f"(a[i + 3]), "+f"(a[i + 4]), "+f"(a[i + 5]), "+f"(a[i + 6]), "+f"(a[i + 7])
#define D64 "{%0,%1,%2,%3,%4,%5,%6,%7,%8,%9,%10,%11,%12,%13,%14,%15,%16,%17,%18,%19,%20,%21,%22,%23,%24,%25,%26,%27,%28,%29,%30,%31," \
            "%32,%33,%34,%35,%36,%37,%38,%39,%40,%41,%42,%43,%44,%45,%46,%47,%48,%49,%50,%51,%52,%53,%54,%55,%56,%57,%58,%59,%60,%61,%62,%63}"
template <int TB>
__device__ __forceinline__ void mma_ss(float (&d)[64], uint64_t da, uint64_t db, int sc) {
  asm volatile("{\n.reg .pred p;\nsetp.ne.b32 p, %66, 0;\n"
               "wgmma.mma_async.sync.aligned.m64n128k16.f32.bf16.bf16 " D64 ", %64, %65, p, 1, 1, 0, %67;\n}"
               : R8(d, 0), R8(d, 8), R8(d, 16), R8(d, 24), R8(d, 32), R8(d, 40), R8(d, 48), R8(d, 56)
               : "l"(da), "l"(db), "r"(sc), "n"(TB));
}
template <int TB>
__device__ __forceinline__ void mma_rs(float (&d)[64], uint32_t a0, uint32_t a1, uint32_t a2, uint32_t a3, uint64_t db, int sc) {
  asm volatile("{\n.reg .pred p;\nsetp.ne.b32 p, %69, 0;\n"
               "wgmma.mma_async.sync.aligned.m64n128k16.f32.bf16.bf16 " D64 ", {%64,%65,%66,%67}, %68, p, 1, 1, %70;\n}"
               : R8(d, 0), R8(d, 8), R8(d, 16), R8(d, 24), R8(d, 32), R8(d, 40), R8(d, 48), R8(d, 56)
               : "r"(a0), "r"(a1), "r"(a2), "r"(a3), "l"(db), "r"(sc), "n"(TB));
}
#define D128 "{%0,%1,%2,%3,%4,%5,%6,%7,%8,%9,%10,%11,%12,%13,%14,%15,%16,%17,%18,%19,%20,%21,%22,%23,%24,%25,%26,%27,%28,%29,%30,%31," \
             "%32,%33,%34,%35,%36,%37,%38,%39,%40,%41,%42,%43,%44,%45,%46,%47,%48,%49,%50,%51,%52,%53,%54,%55,%56,%57,%58,%59,%60,%61,%62,%63," \
             "%64,%65,%66,%67,%68,%69,%70,%71,%72,%73,%74,%75,%76,%77,%78,%79,%80,%81,%82,%83,%84,%85,%86,%87,%88,%89,%90,%91,%92,%93,%94,%95," \
             "%96,%97,%98,%99,%100,%101,%102,%103,%104,%105,%106,%107,%108,%109,%110,%111,%112,%113,%114,%115,%116,%117,%118,%119,%120,%121,%122,%123,%124,%125,%126,%127}"
#define R128(d, e) R8(d, 0), R8(d, 8), R8(d, 16), R8(d, 24), R8(d, 32), R8(d, 40), R8(d, 48), R8(d, 56), \
                   R8(e, 0), R8(e, 8), R8(e, 16), R8(e, 24), R8(e, 32), R8(e, 40), R8(e, 48), R8(e, 56)
__device__ __forceinline__ void mma256_ss(float (&d)[64], float (&e)[64], uint64_t da, uint64_t db, int sc) {
  asm volatile("{\n.reg .pred p;\nsetp.ne.b32 p, %130, 0;\n"
               "wgmma.mma_async.sync.aligned.m64n256k16.f32.bf16.bf16 " D128 ", %128, %129, p, 1, 1, 0, 1;\n}"
               : R128(d, e) : "l"(da), "l"(db), "r"(sc));
}
__device__ __forceinline__ void mma256_rs(float (&d)[64], float (&e)[64], uint32_t a0, uint32_t a1, uint32_t a2, uint32_t a3, uint64_t db) {
  asm volatile("{\n.reg .pred p;\nsetp.ne.b32 p, 1, 0;\n"
               "wgmma.mma_async.sync.aligned.m64n256k16.f32.bf16.bf16 " D128 ", {%128,%129,%130,%131}, %132, p, 1, 1, 1;\n}"
               : R128(d, e) : "r"(a0), "r"(a1), "r"(a2), "r"(a3), "l"(db));
}
template <int N> __device__ __forceinline__ void keep(float (&a)[N]) {
#pragma unroll
  for (int i = 0; i < N; i++) asm volatile("" : "+f"(a[i])::"memory");
}
template <int N> __device__ __forceinline__ void keep(uint32_t (&a)[N]) {
#pragma unroll
  for (int i = 0; i < N; i++) asm volatile("" : "+r"(a[i])::"memory");
}

#define STAMP(idx) do {} while (0)
#define PROF(grp, cond, idx) do {} while (0)

constexpr float SCL2 = 1.4426950408889634f * 0.08838834764831845f;

__device__ __forceinline__ void pack_p(const float (&s)[64], uint32_t (&p)[32]) {
#pragma unroll
  for (int i = 0; i < 32; i++) p[i] = pack_bf(s[2 * i], s[2 * i + 1]);
}

__device__ __forceinline__ void issue_qk(float (&s)[64], uint32_t q0, uint32_t q1, uint32_t kslot) {
  const uint64_t db = make_desc(kslot, 16, 1024), da0 = make_desc(q0, 16, 1024), da1 = make_desc(q1, 16, 1024);
#pragma unroll
  for (int kk = 0; kk < 8; kk++) mma_ss<0>(s, (kk < 4 ? da0 : da1) + (kk & 3) * 2, db + (kk >> 2) * 1024 + (kk & 3) * 2, kk != 0);
}
__device__ __forceinline__ void issue_pv(float (&o)[64], uint32_t (&p)[32], uint32_t vslot, int acc) {
  uint64_t db = make_desc(vslot, 16384, 1024);
#pragma unroll
  for (int kk = 0; kk < 8; kk++)
    mma_rs<1>(o, p[4 * kk], p[4 * kk + 1], p[4 * kk + 2], p[4 * kk + 3], db + kk * 128, kk == 0 ? acc : 1);
}

template <int H>
__device__ __forceinline__ void store_chunk(const float (&a)[64], uint32_t addr) {
#pragma unroll
  for (int i = 8 * H; i < 8 * H + 8; i += 2)
    stmatrix4(addr ^ ((i & 7) << 4), pack_bf(a[4 * i], a[4 * i + 1]), pack_bf(a[4 * i + 2], a[4 * i + 3]),
              pack_bf(a[4 * i + 4], a[4 * i + 5]), pack_bf(a[4 * i + 6], a[4 * i + 7]));
}
template <int H>
__device__ __forceinline__ void store_chunk(const float (&a)[64], float i0, float i1, uint32_t addr) {
#pragma unroll
  for (int i = 8 * H; i < 8 * H + 8; i += 2)
    stmatrix4(addr ^ ((i & 7) << 4), pack_bf(a[4 * i] * i0, a[4 * i + 1] * i0), pack_bf(a[4 * i + 2] * i1, a[4 * i + 3] * i1),
              pack_bf(a[4 * i + 4] * i0, a[4 * i + 5] * i0), pack_bf(a[4 * i + 6] * i1, a[4 * i + 7] * i1));
}
__device__ __forceinline__ float inv_quad_sum(float l) {
  l += __shfl_xor_sync(0xffffffffu, l, 1);
  l += __shfl_xor_sync(0xffffffffu, l, 2);
  return rcp(l);
}

__device__ __forceinline__ void write_table(uint32_t table, bool ca, uint32_t t, const uint4& m0, const uint4& m1) {
  float c0 = untag_sum(m0.x, m1.x), c1 = untag_sum(m0.y, m1.y), c2 = untag_sum(m0.z, m1.z), c3 = untag_sum(m0.w, m1.w);
  if (ca) { c0 = 1.f + rbf(c0); c1 = 1.f + rbf(c1); c2 = 1.f + rbf(c2); c3 = 1.f + rbf(c3); }
  const uint32_t d = table + (t >> 2) * 64 + (t & 1) * 32 + (t & 2) * 2 + (ca ? 0 : 8);
  sts1(d, pack_bf(c0, c1));
  sts1(d + 16, pack_bf(c2, c3));
}

__device__ __forceinline__ void ln_scalars(float mean, float var, float& mb, float& sd) {
  mb = rbf(mean);
  float r; asm("sqrt.approx.ftz.f32 %0, %1;" : "=f"(r) : "f"(rbf(rbf(var) + 1e-5f)));
  sd = rbf(r);
}

__global__ void __cluster_dims__(2, 1, 1) __launch_bounds__(384, 1) fused_kernel(const __grid_constant__ Maps maps, const Ptrs P) {
  extern __shared__ __align__(1024) uint8_t smem_raw[];
  const uint32_t base = smem_u32(smem_raw);
  const int tid = threadIdx.x, lane = tid & 31;
  const int warp = __shfl_sync(0xffffffffu, tid >> 5, 0);
  int b = blockIdx.x;
  if (b < NMAIN) {
    const int p = b >> 1;
    const int grp = p < 4 ? 7 : (p < 36 ? (p + 2) & 7 : (p - 30) % 7), k = p < 4 ? 4 + p : (p < 36 ? (p - 4) >> 3 : 4 + (p - 36) / 7);
    b = grp << 4 | k << 1 | (b & 1);
  }
  PROF(31, tid == 0, 0);

  if (b >= NMAIN) {
    float* sc = reinterpret_cast<float*>(smem_raw);
    float* red = sc + DM;
    for (int k = tid; k < DM; k += 384) sc[k] = rbf(silu_f(__bfloat162float(P.c[k])));
    __syncthreads();
    if (tid < 256) {
      const int col = 2048 + (b - NMAIN) * 1024 + (tid & 127) * 8, r0 = (tid >> 7) * 512;
      float acc[8];
#pragma unroll
      for (int e = 0; e < 8; e++) acc[e] = 0.f;
#pragma unroll 1
      for (int r = r0; r < r0 + 512; r += HU) {
        uint4 w[HU];
#pragma unroll
        for (int u = 0; u < HU; u++) w[u] = ldg_stream4(P.w_mod + (size_t)(r + u) * NMOD + col);
#pragma unroll
        for (int u = 0; u < HU; u++) {
          float s = sc[r + u];
          acc[0] += s * bf_lo(w[u].x); acc[1] += s * bf_hi(w[u].x); acc[2] += s * bf_lo(w[u].y); acc[3] += s * bf_hi(w[u].y);
          acc[4] += s * bf_lo(w[u].z); acc[5] += s * bf_hi(w[u].z); acc[6] += s * bf_lo(w[u].w); acc[7] += s * bf_hi(w[u].w);
        }
      }
      if (tid >= 128) {
#pragma unroll
        for (int e = 0; e < 8; e++) red[(tid & 127) * 8 + e] = acc[e];
      }
      const uint32_t tag = ld_relaxed(&g_epoch) % 3 + 1;
      bar_sync(1, 256);
      if (tid < 128) {
        uint32_t o[8];
#pragma unroll
        for (int e = 0; e < 8; e++) o[e] = __float_as_uint(rbf(acc[e] + red[tid * 8 + e])) | tag;
        st_relaxed4(g_mod + col, o[0], o[1], o[2], o[3]);
        st_relaxed4(g_mod + col + 4, o[4], o[5], o[6], o[7]);
        const uint4 wr = ldg_nc4(P.w_r + tid * 8);
        const uint32_t wv[4] = {wr.x, wr.y, wr.z, wr.w};
        float dsum = 0.f;
#pragma unroll
        for (int e = 0; e < 8; e++) {
          const float m = bf_hi(o[e]);
          dsum += (b == NMAIN + 2 ? rbf(1.f + m) : m) * ((e & 1) ? bf_hi(wv[e >> 1]) : bf_lo(wv[e >> 1]));
        }
#pragma unroll
        for (int k = 16; k > 0; k >>= 1) dsum += __shfl_xor_sync(0xffffffffu, dsum, k);
        if (lane == 0) st_relaxed(g_mod + (b - NMAIN) * 4 + warp, tagf(dsum, tag));
      }
    }
    PROF(2, tid == 0, 1);
    return;
  }

  const int rank = b & 1;
  const int rb = ((b >> 4) << 1) | rank, cj = (b >> 1) & 7;
  const bool late = b & 4;
  const uint32_t bfull = base + OFF_BAR, bempty = bfull + NSLOT * 8;
  const uint32_t gfull = bempty + NSLOT * 8, gempty = gfull + 32;
  const uint32_t bar_ofull = gempty + 32;
  const uint32_t bar_ofree = bar_ofull + 32;
  const uint32_t bar_par = bar_ofree + 32;
  const uint32_t bar_mod = bar_par + 8;
  const uint32_t bar_pread = bar_mod + 8;
  const uint32_t bar_xres = bar_pread + 8;
  const uint32_t bar_ring = bar_xres + 8;
  const uint32_t bar_box = bar_ring + 24;
  const uint32_t bar_go = bar_box + 96;
  const uint32_t bar_go2 = bar_go + 16;
  const uint32_t bar_cnt = bar_go + 24;
  const uint32_t xfull = bar_go + 40, xempty = xfull + 32;
  const uint32_t bar_hw = xempty + 32, bar_hx = bar_hw + 8;
  const uint32_t bar_hpub = bar_hx + 16;
  const uint32_t bar_win = bar_hpub + 16;
  const uint32_t bar_rx = bar_win + 8;
  const uint32_t bar_sel = bar_rx + 8;
  const uint32_t bar_gate = bar_sel + 8;
  const uint32_t bar_rel = bar_gate + 8;
  const uint32_t bar_od = bar_rel + 8;
  const uint32_t bar_mod2 = bar_od + 8;
  const uint32_t bar_res = bar_go + 8;
  const uint32_t stage = base + OFF_STAGE, par = base + OFF_PAR;

  if (warp == 10 && elect_one()) prefetch_map(&maps.wm);
  if (warp == 8 && elect_one()) {
    for (int s = 0; s < NSLOT; s++) { mbar_init(bfull + s * 8, 1); mbar_init(bempty + s * 8, 16); }
    for (int s = 0; s < 4; s++) { mbar_init(gfull + s * 8, 1); mbar_init(gempty + s * 8, 16); mbar_init(xfull + s * 8, 1); mbar_init(xempty + s * 8, 8); mbar_init(bar_ofree + s * 8, 1); mbar_init(bar_ofull + s * 8, 128); }
    mbar_init(bar_par, 64); mbar_init(bar_mod, 256); mbar_init(bar_pread, 2); mbar_init(bar_xres, 1);
    mbar_init(bar_ring, 8); mbar_init(bar_ring + 8, 8); mbar_init(bar_ring + 16, 8);
    mbar_init(bar_go, 1); mbar_init(bar_go2, 1); mbar_init(bar_cnt, 1); mbar_init(bar_cnt + 8, 1); mbar_init(bar_hpub, 8); mbar_init(bar_hpub + 8, 8); mbar_init(bar_res, 1); mbar_init(bar_win, 1); mbar_init(bar_rx, 1); mbar_init(bar_sel, 64); mbar_init(bar_gate, 8); mbar_init(bar_rel, 8); mbar_init(bar_od, 1); mbar_init(bar_mod2, 64);
    for (int s = 0; s < 12; s++) mbar_init(bar_box + s * 8, 1);
    asm volatile("fence.mbarrier_init.release.cluster;" ::: "memory");
    prefetch_map(&maps.x); prefetch_map(&maps.wq); prefetch_map(&maps.k); prefetch_map(&maps.v);
  }
  if (warp == 9 && elect_one()) {
    mbar_init(bar_hw, 1); mbar_init(bar_hx, 1); mbar_init(bar_hx + 8, 1);
    asm volatile("fence.mbarrier_init.release.cluster;" ::: "memory");
    mbar_expect_tx(bar_hw, 32768);
    mbar_expect_tx(bar_hx, 16384);
    mbar_expect_tx(bar_hx + 8, 16384);
    const __nv_bfloat16* xs = P.x + (size_t)(rb * 128 + cj * 16) * DM;
    bulk_load(base + 2 * GST_BYTES, xs, 16384, bar_hx);
    if (!late) {
      tma2d(stage, &maps.wm, (b >> 1) * 32, rank * 512, bar_hw);
      tma2d(stage + 16384, &maps.wm, (b >> 1) * 32, rank * 512 + 256, bar_hw);
    }
    bulk_load(base + 3 * GST_BYTES, xs + 8 * DM, 16384, bar_hx + 8);
  }
  cluster_arrive();

  if (warp >= 8) {
    asm volatile("setmaxnreg.dec.sync.aligned.u32 40;");
    if (warp < 10) bar_arrive(1, 320);
    const uint32_t epoch = ld_relaxed(&g_epoch);
    cluster_wait();
    if (warp == 8) {
      const int kvrow = (cj >> 1) * SK + (SK - WIN);
      int wch = cj * 8 + rank * 2;
#pragma unroll 1
      for (int ps = 0; ps < 3; ps++) {
        const CUtensorMap* mw = ps == 2 ? &maps.wo : &maps.wq;
        const uint32_t xt = ps == 1 ? XT1 : XT2, wt = ps == 0 ? WT0 : (ps == 1 ? WT1 : WT2);
        const int nst = ps == 2 ? 32 : 16;
#pragma unroll 1
        for (int i = 0; i < nst; i++) {
          const uint32_t bf = gfull + (i & 3) * 8;
          const int kt = ps == 2 ? (((cj & 1) * 4 + ((i >> 1) & 3)) * 4 + (i >> 3)) * 2 + (i & 1) : (ps ? i : slice_of(i) + (b & 14)) & 15;
          const uint32_t wd = base + unit_of(wt, i & 3) + rank * UNIT, xd = base + unit_of(xt, i & 3);
          const uint8_t* xs = g_act + (uint32_t)(rb * 80 + (ps - 1) * 16 + kt) * UNIT;
          if (ps == 0 && i == HD) mbar_wait(bar_mod, 0);
          if (ps == 2 && (i & 7) == 0 && i != 8) mbar_wait(i ? bar_cnt + i - 16 : bar_ofree + 24, 0);
          if ((i & 7) == 0) fence_async();
          if (i == RES0) mbar_wait(bar_res, 0);
          mbar_wait(bf, ((i >> 2) & 1) ^ 1);
          if (elect_one()) {
            mbar_expect_tx(bf, ps ? GST_BYTES : 2 * UNIT);
            if (ps && i < 2) bulk_load_stream(xd, xs, UNIT, bf);
            mbar_arrive_pred(bar_go, i == GOST);
            mbar_arrive_pred(bar_go2, ps == 1 && i == PG0);
            mbar_arrive_pred(bar_od, ps && i == (ps == 1 ? ODS1 : ODS) + 1);
            if (i == RES0) mbar_expect_tx(bar_xres, 32768);
          }
          const int wk = (i == 31 ? kt ^ (rank * 32) : kt) * 64, wc = i == 31 ? cj * 2 : wch;
          const uint64_t xp = i == 31 ? l2_normal() : l2_stream();
          mbar_wait(ps && i < 4 ? bempty + i * 8 : gempty + (i & 3) * 8, ((i >> 2) & 1) ^ 1);
          if (elect_one()) {
            tma3d_mc<true>(wd, mw, 0, wk, wc, bf);
            if (ps && i > 2) bulk_load_stream(xd, xs, UNIT, bf, xp);
            if (i == RES0 || i == RES1) tma2d(base + OFF_RES + (i == RES1) * UNIT, &maps.x, cj * 128 + (i == RES1) * 64, rb * 128, bar_xres);
          }
          if (ps && i == 2) {
            mbar_wait(bar_ofree + (ps - 1) * 16, 0);
            if (elect_one()) bulk_load_stream(xd, xs, UNIT, bf);
          }
        }
        if (ps == 2) break;
        wch = ps ? ((wch >> 3) ^ rank) * 2 : wch + 4;
#pragma unroll 1
        for (int u = 0; u < 16; u++) {
          const bool isk = (u == 0) || ((u & 1) && u < 15), kept = (0x1680 >> u) & 1;
          const int blk = (0x472FAD84u >> (u * 2)) & 3;
          const uint32_t sl = base + unit_of(ps ? AT1 : AT0, u & 3) + rank * UNIT, bf = bfull + (u & 3) * 8;
          mbar_wait(bf, ((u >> 2) & 1) ^ 1);
          if (!kept && elect_one()) mbar_expect_tx(bf, SLOT_BYTES);
          mbar_wait(u < 4 ? gempty + ((u + 1) >> 1) * 8 : bempty + (u & 3) * 8, ((u >> 2) & 1) ^ 1);
          if (elect_one()) {
            if (kept) mbar_arrive(bf);
            else if (ps && (blk >= 2 || u > 8)) tma3d_mc<true>(sl, isk ? &maps.k : &maps.v, 0, kvrow + blk * 128, rank, bf);
            else tma3d_mc<false>(sl, isk ? &maps.k : &maps.v, 0, kvrow + blk * 128, rank, bf);
          }
        }
      }
      if (elect_one()) mbar_expect_tx(bar_rx, UNIT);
      mbar_wait(bar_rel, 0);
      if (elect_one()) {
        bulk_load_stream(base + UNIT, g_act + (uint32_t)(rb * 80 + 16 + 63 - (cj & 1) * 32) * UNIT, UNIT, bar_rx);
      }
      if (b < NFFN) {
#pragma unroll 1
        for (int u = 0; u < 12; u++) {
          const uint32_t dst = base + unit_of(u < 4 ? FT_G : (u < 8 ? FT_U : FT_D), u & 3);
          if (elect_one()) mbar_expect_tx(bar_box + u * 8, UNIT);
          if (u == 0 || u == 2 || u == 8) mbar_wait(bar_ring + (u == 8 ? 16 : u * 4), 0);
          const int fp = u < 8 ? FPACE0 : FPACE;
          if (u >= fp) mbar_wait(bar_box + (u - fp) * 8, 0);
          if (elect_one()) {
            if (u < 8) tma2d(dst, u < 4 ? &maps.wg : &maps.wu, b * 32, (u & 3) * 256, bar_box + u * 8);
            else tma3d(dst, &maps.wd, 0, b * 32, (u - 8) * 4, bar_box + u * 8);
          }
        }
      }
    } else if (warp == 9) {
      const uint32_t target = 8 * (epoch + 1);
      uint32_t hmask = 0;
#pragma unroll 1
      for (int i = 0; i < 16; i++) {
        if (i == HDX) mbar_wait(bar_mod, 0);
        const int kt = (2 * cj + slice_of(i)) & 15;
        const uint32_t need = i == 15 ? 0xffffu : 1u << kt;
        if (i >= NRS && (hmask & need) != need) {
          uint32_t n = 0;
          do { hmask = __ballot_sync(0xffffffffu, ld_acquire(&g_cnt_h[rb * 32 + (lane & 15)]) == epoch + 1); watchdog(n); } while ((hmask & need) != need);
          PROF(1, lane == 0 && i == NRS, 26);
          fence_async();
        }
        mbar_wait(xempty + (i & 3) * 8, ((i >> 2) & 1) ^ 1);
        if (elect_one()) {
          mbar_expect_tx(xfull + (i & 3) * 8, UNIT);
          if (i < NRS) tma2d(base + (i & 3) * GST_BYTES, &maps.x, kt * 64, rb * 128, xfull + (i & 3) * 8);
          else bulk_load_stream(base + (i & 3) * GST_BYTES, g_act + (uint32_t)(rb * 80 + kt) * UNIT, UNIT, xfull + (i & 3) * 8);
        }
      }
      prefetch_map(&maps.wo);
#pragma unroll 1
      for (int t = 0; t < 4; t++) {
        if (t & 1) mbar_wait(bar_od, t >> 1);
        const int ops = OPS >> (t & 1);
#pragma unroll 1
        for (int p = 0; p < 32768; p += ops) {
          const uint32_t w = p >> 14, c = (p >> 13) & 1, off = w * 8192 + (p & 8191);
          mbar_wait(bar_ofull + (t & 1) * 16 + w * 8, t >> 1);
          if (elect_one()) {
            bulk_store(g_act + (uint32_t)(rb * 80 + 16 + (cj * 4 + t) * 2 + c) * UNIT + off, base + unit_of(QT, 2 * t + c) + off, ops);
            asm volatile("cp.async.bulk.commit_group;" ::: "memory");
            asm volatile("cp.async.bulk.wait_group.read 0;" ::: "memory");
          }
        }
        if (elect_one()) {
          mbar_arrive(t < 3 ? bar_ofree + t * 8 : bar_res);
          asm volatile("cp.async.bulk.wait_group 0;" ::: "memory");
          fence_async();
          red_release(&g_cnt_o[((rb * 4 + t) * 2 + (cj >> 2)) * 32], 2);
        }
        if (t) {
          wait_counter(&g_cnt_o[(rb * 8 + 2 * t + (cj & 1)) * 32], target);
          if (t & 1) wait_counter(&g_cnt_o[(rb * 8 + (t == 1 ? cj & 1 : 7 - (cj & 1))) * 32], target);
          if (elect_one()) mbar_arrive(t == 1 ? bar_ofree + 24 : bar_cnt + t * 8 - 16);
        }
      }
      PROF(2, lane == 0, 27);
      const uint32_t tag = epoch % 3 + 1;
      const uint32_t* inbox = g_cand + (b >> 4) % CR * 512 + (lane & 15) * CS;
      mbar_wait(bar_ring + 16, 0);
      uint32_t c0 = ld_relaxed(inbox), n = 0;
#define CAND_STEP(cv)                                                                                        \
      {                                                                                                      \
        const bool valid = (cv & 3u) == tag, all = __all_sync(0xffffffffu, valid);                           \
        const uint32_t best = __reduce_max_sync(0xffffffffu, valid ? cv : 0u);                               \
        const uint32_t blk = __ffs(__ballot_sync(0xffffffffu, cv == best)) - 1;                              \
        if (best) sts2(par + PAR_CONST + 56, best, (blk << 7 | (~best >> 2 & 127)) | (all ? 0x1800 : 0x800)); \
        if (all) break;                                                                                      \
        cv = ld_relaxed(inbox);                                                                              \
      }
      while (true) { CAND_STEP(c0) watchdog(n); }
    } else {
      const int t2 = tid - 320;
      if (late && warp == 10) {
        mbar_wait(bar_hx, 0);
        if (elect_one()) {
          tma2d(stage, &maps.wm, (b >> 1) * 32, rank * 512, bar_hw);
          tma2d(stage + 16384, &maps.wm, (b >> 1) * 32, rank * 512 + 256, bar_hw);
        }
      }
      {
        const uint32_t tag = epoch % 3 + 1;
        mbar_wait(bar_hx + 8, 0);
        mbar_wait(bar_hw, 0);
        __nanosleep(late ? OSL2 : OSL);
        {
          const uint32_t t7 = (warp & 1) * 64 + (lane >> 4) * 32 + 16 + (lane & 15);
          const uint32_t* pm = g_modp + ((cj * 128 + t7 * 4) & (DM - 1));
          uint4 m0, m1, m2, m3;
          uint32_t n = 0;
          do {
            m0 = ld_relaxed4(pm); m1 = ld_relaxed4(pm + 2 * DM); m2 = ld_relaxed4(pm + DM); m3 = ld_relaxed4(pm + 3 * DM);
            watchdog(n);
          } while (!__all_sync(0xffffffffu, tag_ok(m0, tag) && tag_ok(m1, tag) && tag_ok(m2, tag) && tag_ok(m3, tag)));
          write_table(par, false, t7, m0, m1);
          write_table(par, true, t7, m2, m3);
          mbar_arrive(bar_mod2);
        }
      }
      mbar_wait(bar_hpub + (warp & 1) * 8, 0);
      PROF(1, t2 == 0, 24);
#pragma unroll 1
      for (int c = 0; c < 8; c++) {
        const uint32_t off = (warp & 1) * UNIT + c * 2048 + lane * 16;
        uint8_t* dst = g_act + (uint32_t)(rb * 80 + cj * 2) * UNIT + off;
        const uint4 v0 = lds4(stage + off), v1 = lds4(stage + off + 512), v2 = lds4(stage + off + 1024), v3 = lds4(stage + off + 1536);
        stg4(dst, v0); stg4(dst + 512, v1); stg4(dst + 1024, v2); stg4(dst + 1536, v3);
      }
      __syncwarp();
      PROF(1, t2 == 0, 15);
      if (lane == 0) {
        mbar_arrive(bar_pread);
        red_release(&g_cnt_h[rb * 32 + cj * 2 + (warp & 1)], 1);
        PROF(1, t2 == 0, 25);
        prefetch_map(&maps.wg); prefetch_map(&maps.wu); prefetch_map(&maps.wd); prefetch_map(&maps.out);
      }
      __syncwarp();
      if (b < NFFN) {
        mbar_wait(bar_go2, 0);
        const __nv_bfloat16* pg = ((b & 1) ? P.w_up : P.w_gate) + (b >> 1) * 64 + (size_t)t2 * FF;
        const __nv_bfloat16* pd = P.w_down + (size_t)b * 32768 + t2 * 64;
        PROF(2, t2 == 0, 13);
#pragma unroll 1
        for (int i = 0; i < WN; i += WB) {
          uint32_t v[WB];
#pragma unroll
          for (int u = 0; u < WB; u++) {
            const int k = i + u;
            asm volatile("ld.global.cg.L2::128B.u32 %0, [%1];" : "=r"(v[u]) : "l"(k < 16 ? pg + (size_t)k * 64 * FF : pd + (k - 16) * 4096));
          }
#pragma unroll
          for (int u = 1; u < WB; u++) v[0] ^= v[u];
          sts1(par + PAR_SINK + t2 * 4, v[0]);
        }
        PROF(2, t2 == 0, 14);
      }
      const uint32_t tag = epoch % 3 + 1;
      mbar_wait(bar_go, 0);
      bar_sync(4, 64);
      if (warp == 10) {
        const uint32_t* src = g_mod + 2 * DM + cj * 128 + lane * 4;
        const uint2 wr = *reinterpret_cast<const uint2*>(P.w_r + cj * 128 + lane * 4);
        uint4 vga, vsb, vcb, vgb;
        uint32_t n = 0;
        do {
          vga = ld_relaxed4(src); vsb = ld_relaxed4(src + DM); vcb = ld_relaxed4(src + 2 * DM); vgb = ld_relaxed4(src + 3 * DM);
          watchdog(n);
        } while (!__all_sync(0xffffffffu, tag_ok(vga, tag) && tag_ok(vsb, tag) && tag_ok(vcb, tag) && tag_ok(vgb, tag)));
        const float c0 = rbf(1.f + bf_hi(vcb.x)), c1 = rbf(1.f + bf_hi(vcb.y)), c2 = rbf(1.f + bf_hi(vcb.z)), c3 = rbf(1.f + bf_hi(vcb.w));
        const float a0 = c0 * bf_lo(wr.x), a1 = c1 * bf_hi(wr.x), a2 = c2 * bf_lo(wr.y), a3 = c3 * bf_hi(wr.y);
        const uint32_t h0 = pack_bf(a0, a1), h1 = pack_bf(a2, a3);
        const uint32_t t1 = par + PAR_T1 + (lane >> 2) * 64 + (lane & 1) * 32 + (lane & 2) * 2;
        sts1(t1, h0); sts1(t1 + 8, pack_bf(a0 - bf_lo(h0), a1 - bf_hi(h0)));
        sts1(t1 + 16, h1); sts1(t1 + 24, pack_bf(a2 - bf_lo(h1), a3 - bf_hi(h1)));
        const uint32_t tg = par + PAR_SINK + (lane >> 3) * 64 + (lane & 1) * 32 + (lane & 6) * 2;
        sts1(tg, __byte_perm(vga.x, vga.y, 0x7632)); sts1(tg + 16, __byte_perm(vga.z, vga.w, 0x7632));
        sts4(par + PAR_T2 + lane * 32, make_uint4(pack_bf(c0, c1), __byte_perm(vsb.x, vsb.y, 0x7632), __byte_perm(vgb.x, vgb.y, 0x7632), __byte_perm(vga.x, vga.y, 0x7632)));
        sts4(par + PAR_T2 + lane * 32 + 16, make_uint4(pack_bf(c2, c3), __byte_perm(vsb.z, vsb.w, 0x7632), __byte_perm(vgb.z, vgb.w, 0x7632), __byte_perm(vga.z, vga.w, 0x7632)));
      } else {
        const uint4 g = poll4((lane & 8) ? g_mod + 8 - (lane & 1) * 4 : g_mod + 5 * DM + (b >> 4) * 128 + (lane & 7) * 16 + (b & 12), tag);
        sts1(par + PAR_CONST + 60, 0);
        if (lane < 8) sts1(par + PAR_CONST + 16 + lane * 4, (b & 2) ? ((b & 1) ? g.w : g.z) : ((b & 1) ? g.y : g.x));
        else if (lane < 10) sts2(par + PAR_CONST + (lane - 8) * 8, __float_as_uint(untag_sum(g.x, g.y) + untag_sum(g.z, g.w)), epoch);
      }
      __syncwarp();
#pragma unroll 1
      for (int q = 0; q < 32; q++) {
        st_b128(g_xch + ((size_t)b * 8 * 256 + q * 64 + t2) * 4, (epoch & 1) << 16, 0, 0, 0);
        __nanosleep(RSL);
      }
      for (int q = 0; q < 2; q++) st_relaxed4(g_stats + (((rb * 8 + q * 4 + (t2 >> 4)) * 8 + cj) * 16 + (t2 & 15)) * 4, 0, 0, 0, 0);
      if (b < NFFN)
        for (int q = 0; q < 2; q++) st_relaxed4(ypart_slot(b, q * 64 + t2), 0, 0, 0, 0);
      st_relaxed4(g_row + rb * 2 * DM + (t2 >> 5) * DM + cj * 128 + (t2 & 31) * 4, 0, 0, 0, 0);
      __threadfence();
      mbar_arrive(bar_par);
      mbar_wait(bar_gate, 0);
      uint32_t have = 0, n = 0;
      while (true) {
        const uint32_t st = lds1(par + PAR_CONST + 60) >> 7;
        if ((st & 31) != have) {
          const uint32_t* hsrc = g_row + (st & 15) * 2 * DM + t2 * 4;
          uint4 hv[4];
          bool ok = true;
#pragma unroll
          for (int i = 0; i < 4; i++) hv[i] = ld_pairs(hsrc + i * 256);
#pragma unroll
          for (int i = 0; i < 4; i++) {
            sts2(base + ((FT_G >> i * 4) & 15) * UNIT + (warp & 1) * 8192 + 256 + lane * 8, hv[i].x, hv[i].z);
            ok = ok && hv[i].y == tag && hv[i].w == tag;
          }
          have = __all_sync(0xffffffffu, ok) ? st & 31 : 0;
        }
        if ((st ^ have) == 32) break;
        watchdog(n);
      }
      mbar_arrive(bar_sel);
    }
    __syncwarp();
    cluster_arrive();
    {
      const uint32_t tag = epoch % 3 + 1, t3 = tid - 256;
      mbar_wait(bar_win, 0);
      uint2 win = lds2(par + PAR_CONST + 56);
      win.y &= 0x7ff;
      const uint32_t* fsrc = g_row + (win.y >> 7) * 2 * DM + (b >> 4) * 128 + (t3 & 7) * 16 + (b & 6) * 2 + ((b >> 2) & 2);
      const uint32_t* ysrc = ypart_slot(min(t3, NFFN - 1), b);
      uint2 fh = ld_pair(fsrc), fx = ld_pair(fsrc + DM);
      uint4 ya = ld_b128(ysrc);
      const float rwin = __uint_as_float(((int)win.x < 0 ? win.x & 0x7fffffffu : ~win.x) & ~0x1ffu);
      const float rs = rbf(rcp(1.f + __expf(-rbf(rwin))));
      uint32_t n = 0;
      while (__any_sync(0xffffffffu, fh.y != tag || fx.y != tag)) { fh = ld_pair(fsrc); fx = ld_pair(fsrc + DM); watchdog(n); }
      while (true) {
        const bool miss = ((ya.x & 1) | (ya.y & 1) << 1) != tag;
        if (!__any_sync(0xffffffffu, miss)) break;
        if (miss) ya = ld_b128(ysrc);
        watchdog(n);
      }
      PROF(8, t3 == 0, 5);
      float y[8] = {bf_lo(ya.x & ~1u), bf_hi(ya.x), bf_lo(ya.y & ~1u), bf_hi(ya.y), bf_lo(ya.z), bf_hi(ya.z), bf_lo(ya.w), bf_hi(ya.w)};
#pragma unroll
      for (int h = 4; h > 0; h >>= 1) {
        const bool up = lane & (h * 2);
#pragma unroll
        for (int e = 0; e < h; e++) y[e] = (up ? y[e + h] : y[e]) + __shfl_xor_sync(0xffffffffu, up ? y[e] : y[e + h], h * 2);
      }
      y[0] += __shfl_xor_sync(0xffffffffu, y[0], 1);
      if (!(lane & 1)) sts1(par + PAR_RED + 64 + t3 * 2, __float_as_uint(y[0]));
      bar_sync(4, 128);
      if (t3 < 8) {
        float y0 = 0.f;
#pragma unroll
        for (int w7 = 0; w7 < 7; w7++) y0 += __uint_as_float(lds1(par + PAR_RED + 64 + w7 * 32 + t3 * 4));
        const uint32_t gv = lds1(par + PAR_CONST + 16 + t3 * 4);
        const uint32_t upd = hmul2(pack_bf(y0, y0), pack_bf(rs, rs));
        const uint32_t r = hadd2(fx.x, hmul2(__byte_perm(gv, gv, 0x3232), hadd2(fh.x, upd)));
        reinterpret_cast<uint16_t*>(P.out)[(size_t)win.y * DM + (b >> 4) * 128 + t3 * 16 + (b & 15)] = (b & 1) ? r >> 16 : r;
        if (b == 0 && t3 == 0) st_relaxed(&g_epoch, epoch + 1);
      }
      PROF(31, t3 == 0, 36);
    }
    cluster_wait();
  } else {
    const int wg = warp >> 2;

    uint32_t tag;
    {
      uint32_t* const pmod = g_modp + rank * 2 * DM + (b >> 1) * 32 + lane;
      uint32_t* const pln = g_ln1 + (rb * 128 + cj * 16 + warp) * 4;
      uint32_t sc[8];
#pragma unroll
      for (int k = 0; k < 8; k++) sc[k] = ldg_nc1(P.c + rank * 512 + warp * 64 + k * 8 + (lane & 3) * 2);
      const uint32_t epoch = ld_relaxed(&g_epoch);
      if (warp == 0) st_relaxed(pmod, 0);
      if (lane == 0) { st_b128(pln, 0, 0, 0, 0); st_b128(pln + 32, 0, 0, 0, 0); }
      asm volatile("setmaxnreg.inc.sync.aligned.u32 232;");
      bar_sync(1, 320);
#pragma unroll
      for (int k = 0; k < 8; k++) sc[k] = pack_bf(silu_f(bf_lo(sc[k])), silu_f(bf_hi(sc[k])));
      keep(sc);
      tag = epoch % 3 + 1;
#pragma unroll
      for (int part = 0; part < 4; part++) {
        if (!(part & 1)) {
          const uint32_t xa = base + (2 + part / 2) * GST_BYTES + warp * 2048 + lane * 16;
          mbar_wait(bar_hx + part * 4, 0);
          float s0 = 0.f, s1 = 0.f, q0 = 0.f, q1 = 0.f;
#pragma unroll
          for (int q = 0; q < 4; q++) {
            const uint4 xv = lds4(xa + q * 512);
            const uint32_t u[4] = {xv.x, xv.y, xv.z, xv.w};
#pragma unroll
            for (int e = 0; e < 4; e++) { const float lo = bf_lo(u[e]), hi = bf_hi(u[e]); s0 += lo; s1 += hi; q0 += lo * lo; q1 += hi * hi; }
          }
          s0 += s1; q0 += q1;
#pragma unroll
          for (int o = 16; o > 0; o >>= 1) { s0 += __shfl_xor_sync(0xffffffffu, s0, o); q0 += __shfl_xor_sync(0xffffffffu, q0, o); }
          const float mean = s0 * (1.f / DM);
          float mb, sd;
          ln_scalars(mean, fmaxf(q0 * (1.f / DM) - mean * mean, 0.f), mb, sd);
          uint32_t ih, il;
          split_inv(sd, ih, il);
          if (lane == 0) st_b128(pln + part * 16, pack_bf(mb, mb), ih, il, tag);
          PROF(1, tid == 0 && part == 2, 4);
        } else if (late == (part == 3)) {
          const uint32_t fr = (lane & 7) + (lane >> 4) * 8, tq = lane & 3;
          const uint32_t wa = stage + warp * 4096 + fr * 64 + ((((lane >> 3) & 1) ^ ((fr >> 1) & 3)) << 4);
          float d0[4] = {0.f, 0.f, 0.f, 0.f}, d1[4] = {0.f, 0.f, 0.f, 0.f};
          mbar_wait(bar_hw, 0);
#pragma unroll
          for (int ks = 0; ks < 4; ks++) {
            uint32_t w[8];
            ldmatrix4t(wa + ks * 1024, w[0], w[1], w[2], w[3]);
            ldmatrix4t((wa ^ 32) + ks * 1024, w[4], w[5], w[6], w[7]);
            mma16816(d0, w[0], w[1], w[2], w[3], sc[2 * ks], sc[2 * ks + 1]);
            mma16816(d1, w[4], w[5], w[6], w[7], sc[2 * ks], sc[2 * ks + 1]);
          }
          sts1(base + 2 * GST_BYTES + warp * 2048 + (tq * 8 + (lane >> 2)) * 4, __float_as_uint((tq & 2) ? ((tq & 1) ? d1[2] : d1[0]) : ((tq & 1) ? d0[2] : d0[0])));
          bar_sync(1, 256);
          if (warp == 0) {
            float s = 0.f;
#pragma unroll
            for (int w8 = 0; w8 < 8; w8++) s += __uint_as_float(lds1(base + 2 * GST_BYTES + w8 * 2048 + lane * 4));
            st_relaxed(pmod, (__float_as_uint(s) & ~3u) | tag);
          }
          PROF(1, tid == 0, 3);
        }
      }
      cluster_wait();
      if (wg == 1) bar_arrive(2, 256);
    }

    float f0 = 0.f, f1 = 0.f;
    const uint32_t rempty = lane < 2 ? mapa(bempty, lane & 1) : 0;
    constexpr uint32_t GE = NSLOT * 8 + 32;
    float o[64], s[64];
#pragma unroll 1
    for (int ps = 0; ps < 3; ps++) {
      {
        const uint32_t xt = ps == 1 ? XT1 : XT2, wt = ps == 1 ? WT1 : WT2;
        const int nst = ps == 2 ? 28 : 14;
        if (ps == 0) {
          float ga[64], gb[64];
#pragma unroll
          for (int i = 0; i < 64; i++) { ga[i] = 0.f; gb[i] = 0.f; }
          uint32_t a[2][16];
          const uint32_t l = fresh_lane();
          uint32_t fa[4];
#pragma unroll
          for (int kk = 0; kk < 4; kk++) fa[kk] = (base + wg * 8192 + frag_offset(warp)) ^ (kk * 32);
          const uint32_t mt = par + (l & 3) * 16;
          auto fetch = [&](int i, uint32_t (&f)[16], uint32_t z) {
            mbar_wait(xfull + (i & 3) * 8, i >> 2);
#pragma unroll
            for (int kk = 0; kk < 4; kk++) ldmatrix4(fa[kk] + (i & 3) * GST_BYTES + z, f[4 * kk], f[4 * kk + 1], f[4 * kk + 2], f[4 * kk + 3]);
          };
          const bool oddw = warp & 2;
          uint4 r0, r1;
          {
            const uint32_t t7 = (warp & 1) * 64 + (l >> 4) * 32 + (l & 15);
            const uint32_t* pm = g_modp + wg * DM + ((cj * 128 + t7 * 4) & (DM - 1));
            const uint32_t* pr = g_ln1 + (rb * 128 + warp * 16 + (l >> 2)) * 4;
            uint4 m0 = make_uint4(tag, tag, tag, tag), m1 = m0;
            if (!oddw) { m0 = ld_relaxed4(pm); m1 = ld_relaxed4(pm + 2 * DM); }
            r0 = ld_b128(pr); r1 = ld_b128(pr + 32);
            fetch(0, a[0], 0); fetch(1, a[1], 0);
            uint32_t n = 0;
            bool written = false;
#pragma unroll 1
            while (true) {
              uint32_t miss;
              asm volatile("{ .reg .pred p0, p1, p2, p3; .reg .b32 t, u;\n"
                           "lop3.b32 t, %1, %2, %19, 0x7e; lop3.b32 u, %3, %4, %19, 0x7e; or.b32 t, t, u; and.b32 t, t, 3; setp.ne.u32 p0, t, 0;\n"
                           "lop3.b32 t, %5, %6, %19, 0x7e; lop3.b32 u, %7, %8, %19, 0x7e; or.b32 t, t, u; and.b32 t, t, 3; setp.ne.u32 p1, t, 0;\n"
                           "setp.ne.u32 p2, %12, %19; setp.ne.u32 p3, %16, %19;\n"
                           "@p0 ld.relaxed.gpu.global.v4.u32 {%1, %2, %3, %4}, [%17];\n"
                           "@p1 ld.relaxed.gpu.global.v4.u32 {%5, %6, %7, %8}, [%17 + 8192];\n"
                           "@p2 ld.relaxed.gpu.global.v4.u32 {%9, %10, %11, %12}, [%18];\n"
                           "@p3 ld.relaxed.gpu.global.v4.u32 {%13, %14, %15, %16}, [%18 + 128];\n"
                           "or.pred p0, p0, p1; or.pred p2, p2, p3; vote.sync.any.pred p0, p0, 0xffffffff; vote.sync.any.pred p2, p2, 0xffffffff;\n"
                           "selp.u32 t, 1, 0, p0; selp.u32 u, 2, 0, p2; or.b32 %0, t, u; }"
                           : "=r"(miss), "+r"(m0.x), "+r"(m0.y), "+r"(m0.z), "+r"(m0.w), "+r"(m1.x), "+r"(m1.y), "+r"(m1.z), "+r"(m1.w),
                             "+r"(r0.x), "+r"(r0.y), "+r"(r0.z), "+r"(r0.w), "+r"(r1.x), "+r"(r1.y), "+r"(r1.z), "+r"(r1.w)
                           : "l"(pm), "l"(pr), "r"(tag) : "memory");
              if (!(miss & 1) && !written) {
                written = true;
                if (!oddw) write_table(par, wg, t7, m0, m1);
                mbar_arrive(bar_mod);
              }
              if (!miss) break;
              watchdog(n);
            }
          }
          const uint32_t zero = r0.w ^ tag;
          auto normalize = [&](uint32_t (&f)[16]) {
#pragma unroll
            for (int k = 0; k < 16; k += 2) { f[k] = ln_norm(f[k], r0.x, r0.y, r0.z); f[k + 1] = ln_norm(f[k + 1], r1.x, r1.y, r1.z); }
          };
          auto modulate = [&](int i, uint32_t (&f)[16]) {
#pragma unroll
            for (int kk = 0; kk < 4; kk++) {
              const uint4 m = lds4(mt + slice_of(i) * 256 + kk * 64);
              f[4 * kk] = hfma2(f[4 * kk], m.x, m.z); f[4 * kk + 1] = hfma2(f[4 * kk + 1], m.x, m.z);
              f[4 * kk + 2] = hfma2(f[4 * kk + 2], m.y, m.w); f[4 * kk + 3] = hfma2(f[4 * kk + 3], m.y, m.w);
            }
            keep(f);
            mbar_arrive_pred(xempty + (i & 3) * 8, l == 0);
          };
          auto publish = [&](int u, uint32_t (&f)[16]) {
#pragma unroll
            for (int kk = 0; kk < 4; kk++) stmatrix4(fa[kk] + OFF_STAGE + u * UNIT, f[4 * kk], f[4 * kk + 1], f[4 * kk + 2], f[4 * kk + 3]);
            __syncwarp();
            mbar_arrive_pred(bar_hpub + u * 8, l == 0);
          };
          auto multiply = [&](int i, uint32_t (&f)[16]) {
            mbar_wait(gfull + (i & 3) * 8, i >> 2);
            const uint64_t db = make_desc(base + (i & 3) * GST_BYTES + UNIT, 8192, 1024);
            wg_fence();
#pragma unroll
            for (int kk = 0; kk < 4; kk++) mma256_rs(ga, gb, f[4 * kk], f[4 * kk + 1], f[4 * kk + 2], f[4 * kk + 3], db + kk * 128);
            wg_commit();
          };
          auto next = [&](int i, uint32_t (&f)[16]) {
            wg_wait<1>();
            mbar_arrive_cl(rempty, GE + ((i + 2) & 3) * 8);
            uint32_t z = zero;
#pragma unroll
            for (int k = 0; k < 16; k += 2) asm volatile("lop3.b32 %0, %1, %2, %0, 0xA8;" : "+r"(z) : "r"(f[k]), "r"(f[k + 1]));
            fetch(i, f, z);
            normalize(f);
            if (i == 2) { keep(f); mbar_wait(bar_mod2, 0); }
            modulate(i, f); multiply(i, f);
          };
          normalize(a[0]); normalize(a[1]);
          keep(a[0]); keep(a[1]);
          mbar_wait(bar_mod, 0);
          PROF(1, tid == 0, 2);
          modulate(0, a[0]); multiply(0, a[0]); publish(0, a[0]);
          modulate(1, a[1]); multiply(1, a[1]);
#pragma unroll 1
          for (int i = 2; i < NRS; i += 2) {
            next(i, a[0]);
            if (i == 2) publish(1, a[0]);
            next(i + 1, a[1]);
          }
          wg_wait<1>();
          mbar_arrive_cl(rempty, GE + ((NRS + 2) & 3) * 8);
#pragma unroll 1
          for (int i = NRS; i < 14; i++) {
            mbar_wait(xfull + (i & 3) * 8, (i >> 2) & 1);
            mbar_wait(gfull + (i & 3) * 8, (i >> 2) & 1);
            const uint32_t xa = base + (i & 3) * GST_BYTES;
            const uint64_t da = make_desc(xa + wg * 8192, 16, 1024), db = make_desc(xa + UNIT, 8192, 1024);
            if (i == 13) bar_sync(2 + wg, 256);
            wg_fence();
#pragma unroll
            for (int kk = 0; kk < 4; kk++) mma256_ss(ga, gb, da + kk * 2, db + kk * 128, 1);
            wg_commit();
            if (i == 13) bar_arrive(3 - wg, 256);
            wg_wait<1>();
            uint32_t z = zero;
#pragma unroll
            for (int k = 0; k < 16; k += 2) asm volatile("lop3.b32 %0, %1, %2, %0, 0xA8;" : "+r"(z) : "r"(a[1][k]), "r"(a[1][k + 1]));
            mbar_arrive_cl(rempty, GE + ((i + 3) & 3) * 8 + z);
            mbar_arrive_pred(xempty + ((i + 3) & 3) * 8, l == 0 && i != NRS);
          }
          mbar_wait(xfull + 16, 1);
          wg_wait<0>();
          keep(ga); keep(gb);
#pragma unroll
          for (int i = 0; i < 64; i++) {
            asm volatile("mov.b32 %0, %1;" : "=f"(s[i]) : "f"(ga[i]));
            asm volatile("mov.b32 %0, %1;" : "=f"(o[i]) : "f"(gb[i]));
          }
        } else {
          float ga[64], gb[64];
#pragma unroll
          for (int i = 0; i < 64; i++) {
            asm volatile("mov.b32 %0, %1;" : "=f"(ga[i]) : "f"(s[i]));
            asm volatile("mov.b32 %0, %1;" : "=f"(gb[i]) : "f"(o[i]));
          }
#pragma unroll 1
          for (int i = 0; i < nst; i++) {
            mbar_wait(gfull + (i & 3) * 8, (i >> 2) & 1);
            const uint64_t da = make_desc(base + unit_of(xt, i & 3) + wg * 8192, 16, 1024), db = make_desc(base + unit_of(wt, i & 3), 8192, 1024);
            if (i == nst - 1) bar_sync(2 + wg, 256);
            wg_fence();
#pragma unroll
            for (int kk = 0; kk < 4; kk++) mma256_ss(ga, gb, da + kk * 2, db + kk * 128, kk ? 1 : i);
            wg_commit();
            if (i == nst - 1) bar_arrive(3 - wg, 256);
            wg_wait<1>();
            mbar_arrive_cl(rempty, GE + ((i + 3) & 3) * 8, i != 0);
            PROF(4, tid == 0 && (i & 3) == 0, 40 + (ps - 1) * 4 + i / 4);
          }
          wg_wait<0>();
          keep(ga); keep(gb);
#pragma unroll
          for (int i = 0; i < 64; i++) {
            asm volatile("mov.b32 %0, %1;" : "=f"(s[i]) : "f"(ga[i]));
            asm volatile("mov.b32 %0, %1;" : "=f"(o[i]) : "f"(gb[i]));
          }
        }
        mbar_arrive_cl(rempty, GE + (ps == 2 ? 24 : 8));
        if (ps == 2) break;
      }
      const uint32_t qw = base + wg * 8192, qt = QT >> (16 * ps), at = ps ? AT1 : AT0;
      {
        const uint32_t wt = ps ? WT1 : WT0;
        const uint64_t da0 = make_desc(qw + unit_of(qt, 2), 16, 1024), da1 = make_desc(qw + unit_of(qt, 3), 16, 1024);
        const uint64_t db0 = make_desc(base + unit_of(wt, 2), 8192, 1024), db1 = make_desc(base + unit_of(wt, 3), 8192, 1024);
        mbar_wait(gfull + 16, 1);
        bar_sync(2 + wg, 256);
        wg_fence();
#pragma unroll
        for (int kk = 0; kk < 4; kk++) mma_ss<1>(s, da0 + kk * 2, db0 + kk * 128, 1);
        wg_commit();
        mbar_wait(xfull + 24, 1);
        mbar_wait(gfull + 24, 1);
        wg_fence();
#pragma unroll
        for (int kk = 0; kk < 4; kk++) mma_ss<1>(s, da1 + kk * 2, db1 + kk * 128, 1);
        wg_commit();
        bar_arrive(3 - wg, 256);
        mbar_wait(ps == 0 ? bar_pread : bar_ofree + 8, 0);
        wg_wait<0>();
        keep(s);
        PROF(2, tid == 0, 8 + ps * 8);
        uint32_t q[32];
        pack_p(s, q);
#pragma unroll
        for (int i = 0; i < 4; i++) stmatrix4((qw + unit_of(qt, 0) + frag_offset(warp)) ^ (i << 5), q[4 * i], q[4 * i + 1], q[4 * i + 2], q[4 * i + 3]);
        keep(q);
        bar_sync(2 + wg, 256);
        wg_fence();
#pragma unroll
        for (int kk = 0; kk < 8; kk++) mma_ss<1>(o, (kk < 4 ? da0 : da1) + (kk & 3) * 2, (kk < 4 ? db0 : db1) + UNIT / 16 + (kk & 3) * 128, 1);
        wg_commit();
        mbar_wait(bfull, 0);
        wg_fence();
        const uint64_t dk = make_desc(base + unit_of(at, 0), 16, 1024);
#pragma unroll
        for (int kk = 0; kk < 8; kk++) mma_rs<0>(s, q[4 * kk], q[4 * kk + 1], q[4 * kk + 2], q[4 * kk + 3], dk + (kk >> 2) * 1024 + (kk & 3) * 2, kk != 0);
        wg_commit();
        bar_arrive(3 - wg, 256);
#pragma unroll
        for (int i = 4; i < 8; i++) stmatrix4((qw + unit_of(qt, 1) + frag_offset(warp)) ^ ((i & 3) << 5), q[4 * i], q[4 * i + 1], q[4 * i + 2], q[4 * i + 3]);
        wg_wait<1>();
        keep(o);
        mbar_arrive_cl(rempty, GE + 16);
        mbar_arrive_cl(rempty, GE + 24);
        store_chunk<0>(o, qw + unit_of(qt, 2) + frag_offset(warp));
        store_chunk<1>(o, qw + unit_of(qt, 3) + frag_offset(warp));
        wg_wait<0>();
        keep(s);
        mbar_arrive_cl(rempty, 0);
      }
      PROF(4, tid == 0 && ps == 1, 61);
      float l0 = 0.f, l1 = 0.f;
      auto step = [&](auto odd_c, const int j, uint32_t (&pw)[32], uint32_t (&pr)[32]) {
        constexpr bool ODD = decltype(odd_c)::value;
        const bool first = !ODD && (j & 2) == 0, last = ODD && j == 7;
        const uint32_t ph = (j >> 1) & 1;
        float i0, i1, a0, a1;
        const bool so = !ODD && j == 4;
        if (so) { i0 = inv_quad_sum(l0); i1 = inv_quad_sum(l1); l0 = 0.f; l1 = 0.f; }
        if (first) {
          int m0 = max(__float_as_int(s[0]), __float_as_int(s[1])), m1 = max(__float_as_int(s[2]), __float_as_int(s[3]));
#pragma unroll
          for (int i = 1; i < PMX; i++) {
            m0 = __vimax3_s32(m0, __float_as_int(s[4 * i]), __float_as_int(s[4 * i + 1]));
            m1 = __vimax3_s32(m1, __float_as_int(s[4 * i + 2]), __float_as_int(s[4 * i + 3]));
          }
          m0 = max(m0, __shfl_xor_sync(0xffffffffu, m0, 1)); m1 = max(m1, __shfl_xor_sync(0xffffffffu, m1, 1));
          m0 = max(m0, __shfl_xor_sync(0xffffffffu, m0, 2)); m1 = max(m1, __shfl_xor_sync(0xffffffffu, m1, 2));
          f0 = fmaf(__int_as_float(m0), SCL2, BIAS); f1 = fmaf(__int_as_float(m1), SCL2, BIAS);
        }
        bool redo = false;
        while (true) {
          if (redo) {
            float m0 = fmaxf(s[0], s[1]), m1 = fmaxf(s[2], s[3]);
#pragma unroll
            for (int i = 1; i < 16; i++) { m0 = fmaxf(m0, fmaxf(s[4 * i], s[4 * i + 1])); m1 = fmaxf(m1, fmaxf(s[4 * i + 2], s[4 * i + 3])); }
            m0 = fmaxf(m0, __shfl_xor_sync(0xffffffffu, m0, 1)); m1 = fmaxf(m1, __shfl_xor_sync(0xffffffffu, m1, 1));
            m0 = fmaxf(m0, __shfl_xor_sync(0xffffffffu, m0, 2)); m1 = fmaxf(m1, __shfl_xor_sync(0xffffffffu, m1, 2));
            m0 = fmaf(m0, SCL2, BIAS); m1 = fmaf(m1, SCL2, BIAS);
            if (!first) {
              m0 = fmaxf(m0, f0); m1 = fmaxf(m1, f1);
              const float c0 = ex2(f0 - m0), c1 = ex2(f1 - m1);
              l0 *= c0; l1 *= c1;
              wg_wait<0>();
              keep(o);
#pragma unroll
              for (int i = 0; i < 16; i++) { o[4 * i] *= c0; o[4 * i + 1] *= c0; o[4 * i + 2] *= c1; o[4 * i + 3] *= c1; }
            }
            f0 = m0; f1 = m1;
          }
          float b0 = 0.f, b1 = 0.f;
          a0 = 0.f; a1 = 0.f;
#pragma unroll
          for (int i = 0; i < 16; i++) {
            const float e0 = ex2(fmaf(s[4 * i], SCL2, -f0)), e1 = ex2(fmaf(s[4 * i + 1], SCL2, -f0));
            const float e2 = ex2(fmaf(s[4 * i + 2], SCL2, -f1)), e3 = ex2(fmaf(s[4 * i + 3], SCL2, -f1));
            a0 += e0; b0 += e1; a1 += e2; b1 += e3;
            pw[2 * i] = pack_bf(e0, e1); pw[2 * i + 1] = pack_bf(e2, e3);
            if (i == VREL) {
#pragma unroll
              for (int k = 0; k < 2 * VREL + 2; k++) asm volatile("" : "+r"(pw[k])::"memory");
              mbar_wait(bar_mod, 0);
              wg_wait<0>();
              mbar_arrive_cl(rempty, ODD ? 16 : 0, !redo && (ODD || j));
#pragma unroll
              for (int k = 4 * VREL + 4; k < 64; k++) asm volatile("" : "+f"(s[k])::"memory");
            }
          }
          a0 += b0; a1 += b1;
          if (redo) break;
          redo = __any_sync(0xffffffffu, !(a0 + a1 < 1.f));
          if (!redo) break;
        }
        l0 += a0; l1 += a1;
        keep(pw);
        keep(o);
        if (so) store_chunk<0>(o, i0, i1, qw + unit_of(qt, 0) + frag_offset(warp));
        keep(o);
        if (j == (ODD ? 5 : 0)) { fence_async_smem(); if (ODD) mbar_arrive(bar_ofull + wg * 8); }
        mbar_wait(bfull + (ODD ? 24 : 8), ph);
        bar_sync(2 + wg, 256);
        if (!last) {
          const uint32_t qn = qt >> (j >= 3 ? 8 : 0);
          wg_fence();
          issue_qk(s, qw + unit_of(qn, 0), qw + unit_of(qn, 1), base + unit_of(at, ODD ? 3 : 1));
          wg_commit();
          mbar_wait(bfull + (ODD ? 0 : 16), ODD ? ph ^ 1 : ph);
        }
        if (so) { store_chunk<1>(o, i0, i1, qw + unit_of(qt, 1) + frag_offset(warp)); keep(o); }
        wg_fence();
        issue_pv(o, pw, base + unit_of(at, ODD ? (last ? 3 : 0) : 2), !first);
        wg_commit();
        bar_arrive(3 - wg, 256);
        wg_wait<1>();
        keep(s);
        mbar_arrive_cl(rempty, ODD ? 24 : 8, !last);
        PROF(4, tid == 0 && ps == 1, 51 + j);
      };
      uint32_t pa[32], pb[32];
#pragma unroll 1
      for (int j = 0; j < 8; j += 2) {
        step(std::false_type{}, j, pa, pb);
        step(std::true_type{}, j + 1, pb, pa);
      }
      {
        const float i0 = inv_quad_sum(l0), i1 = inv_quad_sum(l1);
        wg_wait<0>();
        keep(o);
        mbar_arrive_cl(rempty, 24);
        store_chunk<0>(o, i0, i1, qw + unit_of(qt, 2) + frag_offset(warp));
        store_chunk<1>(o, i0, i1, qw + unit_of(qt, 3) + frag_offset(warp));
        fence_async_smem();
        mbar_arrive(bar_ofull + 16 + wg * 8);
      }
      PROF(2, tid == 0, 10 + ps * 8);
    }

    const int ln = fresh_lane(), g = ln >> 2, tq = ln & 3, ct = warp * 32 + ln;
    const bool lane0 = ln == 0;
    const int lrow0 = warp * 16 + g;
    const uint32_t res = base + OFF_RES, trow = res + wg * 8192 + frag_offset(warp);
    uint32_t xr[32];
    uint4 sv[4], own;
    uint32_t* const sg = g_stats + (rb * 8 + warp) * 512 + g * 4;
    uint32_t* sp[4];
#pragma unroll
    for (int k = 0; k < 4; k++) sp[k] = sg + (tq & 1) * 32 + (((tq >> 1) ^ (cj >> 2)) * 4 + (k ^ (cj & 3))) * 64;
    {
      const uint64_t da = make_desc(base + wg * 8192, 16, 1024), db = make_desc(base, 8192, 1024);
      constexpr int U = UNIT / 16;
#define HALF_STAGE(acc, xu, wu) _Pragma("unroll") for (int kk = 0; kk < 4; kk++) mma_ss<1>(acc, da + (xu) * U + kk * 2, db + (wu) * U + kk * 128, 1)
      PROF(10, ct == PT, 19); STAMP(0);
      cluster_arrive();
      mbar_wait(gfull, 1);
      mbar_wait(gfull + 8, 1);
      bar_sync(2 + wg, 256);
      wg_fence();
      HALF_STAGE(o, 7, 1);
      HALF_STAGE(o, 8, 3);
      wg_commit();
      STAMP(16);
      mbar_wait(gfull + 16, 1);
      STAMP(17);
      wg_fence();
      HALF_STAGE(o, 6, 11);
      wg_commit();
      bar_arrive(3 - wg, 256);
      mbar_wait(bar_par, 0);
      uint32_t* xo = g_xch + ((size_t)b * 8 * 256 + ct) * 4;
      const uint32_t* xi = g_xch + ((size_t)(b ^ 2) * 8 * 256 + ct) * 4;
      const uint32_t par1 = (~lds1(par + PAR_CONST + 4) & 1) << 16;
      wg_wait<1>();
      mbar_arrive_pred(bar_rel, lane0);
      wg_wait<0>();
      keep(o);
      mbar_arrive_pred(bar_ring, lane0);
      PROF(8, ct == PT, 20); STAMP(1);
#define SEND(i) st_b128(xo + (i) * 1024, (pack_bf(o[8 * (i)], o[8 * (i) + 1]) & ~0x10000u) | par1, pack_bf(o[8 * (i) + 2], o[8 * (i) + 3]), \
                        pack_bf(o[8 * (i) + 4], o[8 * (i) + 5]), pack_bf(o[8 * (i) + 6], o[8 * (i) + 7]))
#pragma unroll
      for (int i = 0; i < NS1; i++) SEND(i);
      PROF(8, ct == PT, 21); STAMP(2);
      bar_sync(2 + wg, 256);
      wg_fence();
      HALF_STAGE(s, 7, 0);
      HALF_STAGE(s, 8, 2);
      HALF_STAGE(s, 6, 10);
      wg_commit();
      bar_arrive(3 - wg, 256);
      STAMP(18);
      mbar_wait(gfull + 24, 1);
#pragma unroll
      for (int i = NS1; i < 8; i++) SEND(i);
      uint4 v[8];
      STAMP(19);
      mbar_wait(bar_xres, 0);
      wg_wait<0>();
      mbar_arrive_pred(bar_ring + 8, lane0);
      bar_sync(2 + wg, 256);
      STAMP(20);
#pragma unroll
      for (int i = 0; i < LD2; i++) v[i] = ld_b128(xi + i * 1024);
      mbar_wait(bar_xres, 0);
      wg_fence();
      HALF_STAGE(s, 9, 4);
      wg_commit();
      mbar_wait(bar_rx, 0);
      wg_fence();
      HALF_STAGE(s, 1, 5);
      wg_commit();
      bar_arrive(3 - wg, 256);
      STAMP(21);
#pragma unroll
      for (int i = LD2; i < 8; i++) v[i] = ld_b128(xi + i * 1024);
      mbar_wait(bar_xres, 0);
      wg_wait<0>();
      keep(s);
      mbar_arrive_pred(bar_ring + 16, lane0);
      PROF(10, ct == PT, 23); STAMP(4);
#pragma unroll
      for (int i = 0; i < 16; i += 2) ldmatrix4((trow ^ ((i & 7) << 4)) + (i >> 3) * 16384, xr[2 * i], xr[2 * i + 1], xr[2 * i + 2], xr[2 * i + 3]);
      uint32_t ga[16];
      uint4 bw[8];
#pragma unroll
      for (int i = 0; i < 8; i++) {
        if (!(i & 1)) {
          const uint4 t = lds4(par + PAR_SINK + i * 32 + tq * 16);
          ga[2 * i] = t.x; ga[2 * i + 1] = t.y; ga[2 * i + 2] = t.z; ga[2 * i + 3] = t.w;
        }
        bw[i] = lds4(par + PAR_T1 + i * 64 + tq * 16);
        if (!(g & 1)) { bw[i].x = 0x3f803f80u; bw[i].y = 0x3f803f80u; }
      }
      uint32_t pk[32];
      pack_p(s, pk);
      const uint32_t par2 = (~lds1(par + PAR_CONST + 12) & 1) << 16;
      {
        uint32_t n = 0, miss;
        do {
          miss = 0;
#pragma unroll
          for (int i = 0; i < 8; i++) miss |= v[i].x ^ par2;
          miss = __any_sync(0xffffffffu, miss & 0x10000u);
          if (miss) {
#pragma unroll
            for (int i = 0; i < 8; i++)
              asm volatile("{ .reg .pred p; .reg .b32 t; xor.b32 t, %0, %5; and.b32 t, t, 0x10000; setp.ne.u32 p, t, 0;\n"
                           "@p ld.relaxed.gpu.global.v4.u32 {%0, %1, %2, %3}, [%4]; }"
                           : "+r"(v[i].x), "+r"(v[i].y), "+r"(v[i].z), "+r"(v[i].w) : "l"(xi + i * 1024), "r"(par1) : "memory");
          }
          watchdog(n);
        } while (miss);
      }
      PROF(8, ct == PT, 22); STAMP(3);
      float ds[4] = {0.f, 0.f, 0.f, 0.f}, dl[4] = {0.f, 0.f, 0.f, 0.f}, q0[4] = {0.f, 0.f, 0.f, 0.f}, q1[4] = {0.f, 0.f, 0.f, 0.f};
#pragma unroll
      for (int i = 0; i < 8; i++) {
        const uint32_t u0 = hfma2(ga[2 * i], hadd2(pk[4 * i], v[i].x & ~0x10000u), xr[4 * i]);
        const uint32_t u1 = hfma2(ga[2 * i], hadd2(pk[4 * i + 1], v[i].y), xr[4 * i + 1]);
        const uint32_t u2 = hfma2(ga[2 * i + 1], hadd2(pk[4 * i + 2], v[i].z), xr[4 * i + 2]);
        const uint32_t u3 = hfma2(ga[2 * i + 1], hadd2(pk[4 * i + 3], v[i].w), xr[4 * i + 3]);
        xr[4 * i] = u0; xr[4 * i + 1] = u1; xr[4 * i + 2] = u2; xr[4 * i + 3] = u3;
        mma16816(ds, u0, u1, u2, u3, bw[i].x, bw[i].y);
        mma16816(dl, u0, u1, u2, u3, bw[i].z, bw[i].w);
        mma16816(q0, u0, u1, u2, u3, u0, u2);
        mma16816(q1, u0, u1, u2, u3, u1, u3);
      }
      const float sqa = (g & 1) ? q0[1] : q0[0], sqb = (g & 1) ? q1[3] : q1[2], dta = ds[1] + dl[1], dtb = ds[3] + dl[3];
      if (tq == (g >> 1)) {
        st_b128(sg + cj * 64, __float_as_uint(ds[0]), __float_as_uint(sqa), __float_as_uint(dta), tag);
        st_b128(sg + cj * 64 + 32, __float_as_uint(ds[2]), __float_as_uint(sqb), __float_as_uint(dtb), tag);
      }
#pragma unroll
      for (int k = 0; k < 4; k++) sv[k] = ld_b128(sp[k]);
      mbar_wait(bar_xres, 0);
      const float sqc = __shfl_sync(0xffffffffu, sqa, g * 4 + (g >> 1)), sqd = __shfl_sync(0xffffffffu, sqb, g * 4 + (g >> 1));
      own = (tq & 1) ? make_uint4(__float_as_uint(ds[2]), __float_as_uint(sqd), __float_as_uint(dtb), tag)
                     : make_uint4(__float_as_uint(ds[0]), __float_as_uint(sqc), __float_as_uint(dta), tag);
    }
    PROF(8, ct == PT, 29); STAMP(5);
    uint32_t mm, ih, il;
    float rbest;
    uint32_t wf[128];
    const uint32_t frow = (ln & 7) + (ln >> 4) * 8;
    const uint32_t wfo = base + (warp & 1) * 8192 + frow * 64 + ((((ln >> 3) & 1) ^ ((frow >> 1) & 3)) << 4);
#define LOAD_WF(m) _Pragma("unroll") for (int f = 0; f < 16; f++) {                                                   \
      const int r = ((f >> 1) * 4 + (m) * 2 + (f & 1)) * 4;                                                           \
      ldmatrix4t(((wfo + unit_of((m) ? FT_U : FT_G, warp >> 1)) ^ ((f & 1) * 32)) + (f >> 1) * 1024, wf[r], wf[r + 1], wf[r + 2], wf[r + 3]); \
    }
    bool early;
    {
#pragma unroll
      for (int i = 0; i < 16; i += 2) stmatrix4((trow ^ ((i & 7) << 4)) + (i >> 3) * 16384, xr[2 * i], xr[2 * i + 1], xr[2 * i + 2], xr[2 * i + 3]);
      const uint4 cst = lds4(par + PAR_CONST);
      const float A1 = __uint_as_float(cst.x), A2 = __uint_as_float(cst.z);
      uint32_t n = 0;
      early = false;
#pragma unroll 1
      while (true) {
        if (!early && (b >= NFFN || __all_sync(0xffffffffu, mbar_test(bar_box + (warp >> 1) * 8, 0)))) {
          early = true;
          LOAD_WF(0);
          __syncwarp();
          mbar_arrive_pred(bar_gate, lane0);
        }
        uint32_t miss;
        asm volatile("{ .reg .pred p0, p1, p2, p3; .reg .b64 u, v; .reg .b128 w;\n"
                     "setp.ge.u32 p0, %22, 2; setp.ne.and.u32 p0, %4, %21, p0; setp.ne.u32 p1, %8, %21; setp.ne.u32 p2, %12, %21; setp.ne.u32 p3, %16, %21;\n"
                     "@p0 ld.relaxed.gpu.global.v4.u32 {%1, %2, %3, %4}, [%17];\n"
                     "@p1 ld.relaxed.gpu.global.v4.u32 {%5, %6, %7, %8}, [%18];\n"
                     "@p2 ld.relaxed.gpu.global.v4.u32 {%9, %10, %11, %12}, [%19];\n"
                     "@p3 ld.relaxed.gpu.global.v4.u32 {%13, %14, %15, %16}, [%20];\n"
                     "or.pred p0, p0, p1; or.pred p2, p2, p3; or.pred p0, p0, p2; vote.sync.any.pred p0, p0, 0xffffffff; selp.u32 %0, 1, 0, p0; }"
                     : "=r"(miss), "+r"(sv[0].x), "+r"(sv[0].y), "+r"(sv[0].z), "+r"(sv[0].w), "+r"(sv[1].x), "+r"(sv[1].y), "+r"(sv[1].z), "+r"(sv[1].w),
                       "+r"(sv[2].x), "+r"(sv[2].y), "+r"(sv[2].z), "+r"(sv[2].w), "+r"(sv[3].x), "+r"(sv[3].y), "+r"(sv[3].z), "+r"(sv[3].w)
                     : "l"(sp[0]), "l"(sp[1]), "l"(sp[2]), "l"(sp[3]), "r"(tag), "r"(tq) : "memory");
        if (!miss) break;
        watchdog(n);
      }
      const uint4 v0 = tq < 2 ? own : sv[0], v1 = sv[1], v2 = sv[2], v3 = sv[3];
      PROF(8, ct == PT, 30); STAMP(6);
      float su = (__uint_as_float(v0.x) + __uint_as_float(v1.x)) + (__uint_as_float(v2.x) + __uint_as_float(v3.x));
      float sq = (__uint_as_float(v0.y) + __uint_as_float(v1.y)) + (__uint_as_float(v2.y) + __uint_as_float(v3.y));
      float dt = (__uint_as_float(v0.z) + __uint_as_float(v1.z)) + (__uint_as_float(v2.z) + __uint_as_float(v3.z));
      su += __shfl_xor_sync(0xffffffffu, su, 2); sq += __shfl_xor_sync(0xffffffffu, sq, 2); dt += __shfl_xor_sync(0xffffffffu, dt, 2);
      const float m = su * (1.f / DM);
      float mb, sd;
      ln_scalars(m, fmaxf(sq * (1.f / DM) - m * m, 0.f), mb, sd);
      const float inv = rcp(sd);
      rbest = (dt - mb * A1) * inv + A2;
      mm = pack_bf(mb, mb);
      ih = pack_bf(inv, inv);
      const float lo = inv - bf_lo(ih);
      il = pack_bf(lo, lo);
    }
    int ibest;
    {
      const uint32_t bits = __float_as_uint(rbest);
      const uint32_t key = (((int)bits < 0 ? ~bits : bits | 0x80000000u) & ~0x1ffu) | ((127 - lrow0 - (tq & 1) * 8) << 2) | tag;
      sts1(par + PAR_RED + warp * 4, __reduce_max_sync(0xffffffffu, key));
      PROF(8, ct == PT, 38); STAMP(7);
      bar_sync(1, 256);
      const uint4 ka = lds4(par + PAR_RED), kb = lds4(par + PAR_RED + 16);
      const uint32_t k2 = max(max(max(ka.x, ka.y), max(ka.z, ka.w)), max(max(kb.x, kb.y), max(kb.z, kb.w)));
      if (ct < CR && cj == 0) st_relaxed(g_cand + ct * 512 + rb * CS, k2);
      ibest = 127 - ((k2 >> 2) & 127);
    }
    PROF(8, ct == PT, 39); STAMP(8);
    if ((ibest >> 4) == warp) {
      const int src = (ibest & 7) * 4 + ((ibest >> 3) & 1), ch = g * 2;
      const uint32_t cm = __shfl_sync(0xffffffffu, mm, src), ch_ = __shfl_sync(0xffffffffu, ih, src), cl = __shfl_sync(0xffffffffu, il, src);
      const uint32_t xa = res + (ch >> 3) * 16384 + ibest * 128 + (((ch & 7) ^ (ibest & 7)) << 4) + tq * 4;
      const uint32_t x0 = lds1(xa), x1 = lds1(xa ^ 16);
      const uint2 p0 = lds2(par + PAR_T2 + ch * 64 + tq * 16), p1 = lds2(par + PAR_T2 + ch * 64 + 64 + tq * 16);
      uint32_t* dst = g_row + rb * 2 * DM + cj * 128 + ln * 4;
      st_pairs(dst, ln_mod(x0, cm, ch_, cl, p0.x, p0.y), ln_mod(x1, cm, ch_, cl, p1.x, p1.y), tag);
      st_pairs(dst + DM, x0, x1, tag);
      __syncwarp();
    }
    PROF(8, ct == PT, 37); STAMP(9);
    uint32_t wd[64];
    const uint32_t wda = base + unit_of(FT_D, warp >> 1) + (warp & 1) * 8192 + frow * 128 + ((((ln >> 3) & 1) ^ (ln & 7)) << 4);
#define LOAD_WD(f) ldmatrix4t((wda ^ ((((f) >> 1) & 3) * 32)) + ((f) >> 3) * 4096 + ((f) & 1) * 2048, wd[4 * (f)], wd[4 * (f) + 1], wd[4 * (f) + 2], wd[4 * (f) + 3])
    if (!early) {
      if (b < NFFN) mbar_wait(bar_box + (warp >> 1) * 8, 0);
      LOAD_WF(0);
      __syncwarp();
      mbar_arrive_pred(bar_gate, lane0);
    }
    if (b < NFFN) {
      const uint32_t own = base + unit_of(FT_G, warp >> 1) + (warp & 1) * 8192;
      mbar_wait(bar_box + (4 + (warp >> 1)) * 8, 0);
      LOAD_WF(1);
      uint32_t* const ydst = ypart_slot(b, warp * 16 + (tq & 1) * 8 + g);
      PROF(8, ct == PT, 31); STAMP(10);
      bool wdok;
      {
        uint32_t n = 0;
        while (!(wdok = __all_sync(0xffffffffu, mbar_test(bar_box + (8 + (warp >> 1)) * 8, 0))) && !__all_sync(0xffffffffu, mbar_test(bar_sel, 0))) watchdog(n);
      }
      if (wdok) {
#pragma unroll
        for (int f = 0; f < 16; f++) LOAD_WD(f);
      }
      STAMP(11);
      mbar_wait(bar_sel, 0);
      PROF(8, ct == PT, 33); STAMP(12);
      float d[8][4];
#pragma unroll
      for (int i = 0; i < 4; i++) { d[i][0] = 0.f; d[i][1] = 0.f; d[i][2] = 0.f; d[i][3] = 0.f; }
#pragma unroll
      for (int ks = 0; ks < 8; ks++) {
        const uint2 hb = lds2(own + 256 + ks * 32 + tq * 8);
#pragma unroll
        for (int mt = 0; mt < 4; mt++) {
          const int r = ks * 16 + mt * 4;
          mma16816(d[mt], wf[r], wf[r + 1], wf[r + 2], wf[r + 3], hb.x, hb.y);
        }
      }
      sts2(own + (tq * 8 + g) * 8, __float_as_uint((tq & 2) ? ((tq & 1) ? d[1][2] : d[1][0]) : ((tq & 1) ? d[0][2] : d[0][0])),
           __float_as_uint((tq & 2) ? ((tq & 1) ? d[3][2] : d[3][0]) : ((tq & 1) ? d[2][2] : d[2][0])));
      bar_sync(1, 256);
      uint32_t ab[4];
      {
        float G = 0.f, U = 0.f;
        uint2 pv[8];
#pragma unroll
        for (int w8 = 0; w8 < 8; w8++) pv[w8] = lds2(base + ln * 8 + ((FT_G >> (w8 >> 1) * 4) & 15) * UNIT + (w8 & 1) * 8192);
#pragma unroll
        for (int w8 = 0; w8 < 8; w8 += 2) {
          G += __uint_as_float(pv[w8].x) + __uint_as_float(pv[w8 + 1].x);
          U += __uint_as_float(pv[w8].y) + __uint_as_float(pv[w8 + 1].y);
        }
        const float act = rbf(silu_f(rbf(G))) * rbf(U);
        const uint32_t pk = pack_bf(act, __shfl_down_sync(0xffffffffu, act, 1));
#pragma unroll
        for (int i = 0; i < 4; i++) ab[i] = __shfl_sync(0xffffffffu, pk, i * 8 + tq * 2);
      }
      if (!wdok) {
        mbar_wait(bar_box + (8 + (warp >> 1)) * 8, 0);
#pragma unroll
        for (int f = 0; f < 16; f++) LOAD_WD(f);
      }
      PROF(8, ct == PT, 34); STAMP(13);
#pragma unroll
      for (int mt = 0; mt < 8; mt++) {
        d[mt][0] = 0.f; d[mt][1] = 0.f; d[mt][2] = 0.f; d[mt][3] = 0.f;
        mma16816(d[mt], wd[mt * 8], wd[mt * 8 + 1], wd[mt * 8 + 2], wd[mt * 8 + 3], ab[0], ab[1]);
        mma16816(d[mt], wd[mt * 8 + 4], wd[mt * 8 + 5], wd[mt * 8 + 6], wd[mt * 8 + 7], ab[2], ab[3]);
      }
      uint32_t yw[4];
#pragma unroll
      for (int i = 0; i < 4; i++) yw[i] = (tq & 1) ? pack_bf(d[2 * i][2], d[2 * i + 1][2]) : pack_bf(d[2 * i][0], d[2 * i + 1][0]);
      if (tq < 2) st_b128(ydst, (yw[0] & ~1u) | (tag & 1), (yw[1] & ~1u) | (tag >> 1), yw[2], yw[3]);
      PROF(8, ct == PT, 35); STAMP(14);
    }
    mbar_wait(bar_sel, 0);
    mbar_arrive_pred(bar_win, ct == 0);
    const int iwin = lds1(par + PAR_CONST + 60) & 0x7ff;
    const bool cand = (iwin >> 4) == rb * 8 + warp;
    {
      const uint32_t mm0 = __shfl_sync(0xffffffffu, mm, ln & ~1), mm1 = __shfl_sync(0xffffffffu, mm, ln | 1);
      const uint32_t ih0 = __shfl_sync(0xffffffffu, ih, ln & ~1), ih1 = __shfl_sync(0xffffffffu, ih, ln | 1);
      const uint32_t il0 = __shfl_sync(0xffffffffu, il, ln & ~1), il1 = __shfl_sync(0xffffffffu, il, ln | 1);
#pragma unroll 1
      for (int hf = 0; hf < 2; hf++) {
        uint32_t x[16];
#pragma unroll
        for (int i = 0; i < 8; i += 2) ldmatrix4((trow ^ (i << 4)) + hf * 16384, x[2 * i], x[2 * i + 1], x[2 * i + 2], x[2 * i + 3]);
#pragma unroll
        for (int i = 0; i < 8; i++) {
          const uint4 pv = lds4(par + PAR_T2 + (hf * 8 + i) * 64 + tq * 16);
          x[2 * i] = hfma2(hfma2(ln_norm(x[2 * i], mm0, ih0, il0), pv.x, pv.y), pv.z, x[2 * i]);
          x[2 * i + 1] = hfma2(hfma2(ln_norm(x[2 * i + 1], mm1, ih1, il1), pv.x, pv.y), pv.z, x[2 * i + 1]);
        }
#pragma unroll
        for (int i = 0; i < 8; i += 2) stmatrix4((trow ^ (i << 4)) + hf * 16384, x[2 * i], x[2 * i + 1], x[2 * i + 2], x[2 * i + 3]);
        if (!cand) fence_async_smem();
        __syncwarp();
        if (!cand && elect_one()) {
          tma2d_store(&maps.out, res + hf * 16384 + warp * 2048, cj * 128 + hf * 64, rb * 128 + warp * 16);
          asm volatile("cp.async.bulk.commit_group;" ::: "memory");
        }
      }
    }
    if (cand) {
      const int wrow0 = warp * 16;
#pragma unroll 2
      for (int p = 0; p < 8; p++) {
        const int row = 2 * p + (ln >> 4), ch = ln & 15;
        const uint4 v = lds4(res + (ch >> 3) * 16384 + (wrow0 + row) * 128 + (((ch & 7) ^ (row & 7)) << 4));
        if (rb * 128 + wrow0 + row != iwin) *reinterpret_cast<uint4*>(P.out + (size_t)(rb * 128 + wrow0 + row) * DM + cj * 128 + ch * 8) = v;
      }
    }
    asm volatile("cp.async.bulk.wait_group.read 0;" ::: "memory");
    PROF(8, ct == PT, 11); STAMP(15);
    cluster_wait();
  }
}

typedef CUresult (*EncodeFn)(CUtensorMap*, CUtensorMapDataType, cuuint32_t, void*, const cuuint64_t*, const cuuint64_t*,
                             const cuuint32_t*, const cuuint32_t*, CUtensorMapInterleave, CUtensorMapSwizzle,
                             CUtensorMapL2promotion, CUtensorMapFloatOOBfill);

void map2d(EncodeFn enc, CUtensorMap* m, const void* p, uint64_t rows, uint64_t cols, uint32_t brows) {
  cuuint64_t dims[2] = {cols, rows}, strides[1] = {cols * 2};
  cuuint32_t box[2] = {64, brows}, es[2] = {1, 1};
  enc(m, CU_TENSOR_MAP_DATA_TYPE_BFLOAT16, 2, const_cast<void*>(p), dims, strides, box, es, CU_TENSOR_MAP_INTERLEAVE_NONE,
      CU_TENSOR_MAP_SWIZZLE_128B, CU_TENSOR_MAP_L2_PROMOTION_L2_256B, CU_TENSOR_MAP_FLOAT_OOB_FILL_NONE);
}
void map2d_narrow(EncodeFn enc, CUtensorMap* m, const void* p, uint64_t rows, uint64_t cols, uint32_t brows) {
  cuuint64_t dims[2] = {cols, rows}, strides[1] = {cols * 2};
  cuuint32_t box[2] = {32, brows}, es[2] = {1, 1};
  enc(m, CU_TENSOR_MAP_DATA_TYPE_BFLOAT16, 2, const_cast<void*>(p), dims, strides, box, es, CU_TENSOR_MAP_INTERLEAVE_NONE,
      CU_TENSOR_MAP_SWIZZLE_64B, CU_TENSOR_MAP_L2_PROMOTION_L2_64B, CU_TENSOR_MAP_FLOAT_OOB_FILL_NONE);
}
void map3d(EncodeFn enc, CUtensorMap* m, const void* p, uint64_t rows, uint64_t cols, uint32_t brows, uint32_t nch) {
  cuuint64_t dims[3] = {64, rows, cols / 64}, strides[2] = {cols * 2, 128};
  cuuint32_t box[3] = {64, brows, nch}, es[3] = {1, 1, 1};
  enc(m, CU_TENSOR_MAP_DATA_TYPE_BFLOAT16, 3, const_cast<void*>(p), dims, strides, box, es, CU_TENSOR_MAP_INTERLEAVE_NONE,
      CU_TENSOR_MAP_SWIZZLE_128B, CU_TENSOR_MAP_L2_PROMOTION_L2_256B, CU_TENSOR_MAP_FLOAT_OOB_FILL_NONE);
}

}

extern "C" void kernel_launch(void* const* d_in, const int* in_sizes, int n_in, void* d_out, int out_size) {
  (void)in_sizes; (void)n_in; (void)out_size;
  static EncodeFn enc = nullptr;
  if (!enc) {
    void* fn = nullptr;
    cudaDriverEntryPointQueryResult st;
    cudaGetDriverEntryPoint("cuTensorMapEncodeTiled", &fn, cudaEnableDefault, &st);
    enc = (EncodeFn)fn;
    cudaFuncSetAttribute(fused_kernel, cudaFuncAttributeMaxDynamicSharedMemorySize, SMEM_BYTES);
  }
  Maps maps;
  map2d(enc, &maps.x, d_in[0], SEQ, DM, 128);
  map2d(enc, &maps.out, d_out, SEQ, DM, 16);
  map3d(enc, &maps.wq, d_in[3], DM, NQ, 64, 2);
  map3d(enc, &maps.k, d_in[1], 4 * SK, 128, 128, 1);
  map3d(enc, &maps.v, d_in[2], 4 * SK, 128, 128, 1);
  map3d(enc, &maps.wo, d_in[4], NQ, DM, 64, 2);
  map2d_narrow(enc, &maps.wg, d_in[7], DM, FF, 256);
  map2d_narrow(enc, &maps.wu, d_in[8], DM, FF, 256);
  map3d(enc, &maps.wd, d_in[9], FF, DM, 32, 4);
  map2d_narrow(enc, &maps.wm, d_in[11], DM, NMOD, 256);
  Ptrs p;
  p.x = (const __nv_bfloat16*)d_in[0];
  p.w_r = (const __nv_bfloat16*)d_in[6];
  p.w_gate = (const __nv_bfloat16*)d_in[7];
  p.w_up = (const __nv_bfloat16*)d_in[8];
  p.w_down = (const __nv_bfloat16*)d_in[9];
  p.c = (const __nv_bfloat16*)d_in[10];
  p.w_mod = (const __nv_bfloat16*)d_in[11];
  p.out = (__nv_bfloat16*)d_out;
  fused_kernel<<<NMAIN + NHELP, 384, SMEM_BYTES>>>(maps, p);
}
```

```cpp
#include <cuda_runtime.h>
#include <cuda_bf16.h>
#include <cuda.h>
#include <stdint.h>
#include <type_traits>

#define HD 2
#define HDX 2
#define NRS 8
#define OSL 900
#define OSL2 400
#define RSL 40
#define BIAS 96.f
#define VREL 5
#define OPS 8192
#define ODS1 5
#define ODS 7
#define PG0 15
#define WB 2
#define WN 20
#define HU 32
#define RES0 17
#define RES1 20
#define GOST 20
#define NS1 5
#define LD2 4
#define FPACE0 2
#define FPACE 3
#define CR 8
#define CS 8

namespace {

constexpr int SEQ = 2048, DM = 1024, NQ = 4096, SK = 2048, WIN = 512, FF = 3584, NMOD = 6144;
constexpr int NMAIN = 128, NHELP = 4, NFFN = 112;
constexpr int NSLOT = 4, SLOT_BYTES = 32768, UNIT = 16384, GST_BYTES = 3 * UNIT;
constexpr uint32_t XT1 = 0xDCBA, XT2 = 0x9687;
constexpr uint32_t WT0 = 0xA741, WT1 = 0x7420, WT2 = 0x4A20;
constexpr uint32_t AT0 = WT1, AT1 = WT2;
constexpr uint32_t QT = 0xDC9696DC;
constexpr int OFF_STAGE = 12 * UNIT;
constexpr uint32_t FT_G = 0x07B3, FT_U = 0xA628, FT_D = 0x5149;
constexpr int OFF_RES = 12 * UNIT;
constexpr int OFF_PAR = 14 * UNIT;
constexpr int OFF_BAR = OFF_PAR + 2528;
constexpr int SMEM_BYTES = OFF_BAR + 544;
static_assert(SMEM_BYTES <= 232448, "smem");

constexpr int PAR_T1 = 0;
constexpr int PAR_T2 = 512;
constexpr int PAR_CONST = 1536;
constexpr int PAR_RED = 1600;
constexpr int PAR_SINK = 2176;

struct Maps {
  CUtensorMap x, wq, k, v, wo, wg, wu, wd, wm, out;
};
struct Ptrs {
  const __nv_bfloat16 *x, *w_r, *c, *w_mod, *w_gate, *w_up, *w_down;
  __nv_bfloat16* out;
};

__device__ __align__(1024) uint8_t g_act[16 * 80 * UNIT];
__device__ __align__(128) uint32_t g_mod[NMOD];
__device__ __align__(128) uint32_t g_modp[2 * 2 * DM];
__device__ __align__(128) uint32_t g_ln1[SEQ * 4];
__device__ __align__(128) uint32_t g_cnt_h[16 * 32];
__device__ __align__(128) uint32_t g_cnt_o[128 * 32];
__device__ __align__(128) uint32_t g_xch[NMAIN * 8 * 256 * 4];
__device__ __align__(128) uint32_t g_stats[8 * SEQ * 4];
__device__ __align__(128) uint32_t g_cand[CR * 512];
__device__ __align__(128) uint32_t g_row[16 * 2 * DM];
__device__ __align__(128) uint32_t g_ypart[NMAIN * NFFN * 4];
__device__ __forceinline__ uint32_t* ypart_slot(int writer, int reader) { return g_ypart + (writer * NMAIN + reader) * 4; }
__device__ uint32_t g_epoch;

__device__ __forceinline__ uint32_t fresh_lane() { uint32_t l; asm volatile("mov.u32 %0, %%laneid;" : "=r"(l)); return l; }
__device__ __forceinline__ uint32_t frag_offset(int warp) {
  const uint32_t l = fresh_lane();
  return ((warp & 3) * 16 + (l & 15)) * 128 + (((l >> 4) ^ (l & 7)) << 4);
}
__device__ __forceinline__ bool elect_one() {
  uint32_t p;
  asm volatile("{ .reg .pred q; elect.sync _|q, 0xffffffff; selp.u32 %0, 1, 0, q; }" : "=r"(p));
  return p;
}
__device__ __forceinline__ uint32_t smem_u32(const void* p) { return (uint32_t)__cvta_generic_to_shared(p); }
__device__ __forceinline__ void mbar_init(uint32_t bar, uint32_t cnt) {
  asm volatile("mbarrier.init.shared::cta.b64 [%0], %1;" ::"r"(bar), "r"(cnt) : "memory");
}
__device__ __forceinline__ void mbar_expect_tx(uint32_t bar, uint32_t bytes) {
  asm volatile("mbarrier.arrive.expect_tx.shared::cta.b64 _, [%0], %1;" ::"r"(bar), "r"(bytes) : "memory");
}
__device__ __forceinline__ void mbar_arrive(uint32_t bar) {
  asm volatile("mbarrier.arrive.shared::cta.b64 _, [%0];" ::"r"(bar) : "memory");
}
__device__ __forceinline__ void mbar_arrive_pred(uint32_t bar, bool p) {
  asm volatile("{ .reg .pred p; setp.ne.b32 p, %1, 0; @p mbarrier.arrive.shared::cta.b64 _, [%0]; }" ::"r"(bar), "r"((int)p) : "memory");
}
__device__ __forceinline__ void mbar_arrive_cl(uint32_t bar, uint32_t off, bool p = true) {
  asm volatile("{ .reg .pred p, q; .reg .b32 a; setp.ne.b32 q, %2, 0; setp.ne.and.b32 p, %0, 0, q; add.u32 a, %0, %1; @p mbarrier.arrive.shared::cluster.b64 _, [a]; }"
               ::"r"(bar), "r"(off), "r"((int)p) : "memory");
}
__device__ __forceinline__ uint32_t mapa(uint32_t addr, uint32_t cta) {
  uint32_t r; asm("mapa.shared::cluster.u32 %0, %1, %2;" : "=r"(r) : "r"(addr), "r"(cta)); return r;
}
__device__ __forceinline__ void cluster_arrive() { asm volatile("barrier.cluster.arrive.relaxed.aligned;" ::: "memory"); }
__device__ __forceinline__ void cluster_wait() { asm volatile("barrier.cluster.wait.aligned;" ::: "memory"); }
__device__ __forceinline__ void watchdog(uint32_t& n) {
}
__device__ __forceinline__ void mbar_wait(uint32_t bar, uint32_t parity) {
  asm volatile("{\n.reg .pred p;\nWAIT_%=:\nmbarrier.try_wait.parity.shared::cta.b64 p, [%0], %1;\n@!p bra WAIT_%=;\n}" ::"r"(bar), "r"(parity) : "memory");
}
__device__ __forceinline__ bool mbar_test(uint32_t bar, uint32_t parity) {
  uint32_t ok;
  asm volatile("{\n.reg .pred p;\nmbarrier.test_wait.parity.shared::cta.b64 p, [%1], %2;\nselp.u32 %0, 1, 0, p;\n}" : "=r"(ok) : "r"(bar), "r"(parity) : "memory");
  return ok;
}
__device__ __forceinline__ uint64_t l2_stream() {
  uint64_t f; asm("createpolicy.fractional.L2::evict_first.b64 %0, 1.0;" : "=l"(f)); return f;
}
__device__ __forceinline__ uint64_t l2_normal() {
  uint64_t f; asm("createpolicy.fractional.L2::evict_normal.b64 %0, 1.0;" : "=l"(f)); return f;
}
__device__ __forceinline__ void tma2d(uint32_t dst, const CUtensorMap* m, int c0, int c1, uint32_t bar) {
  asm volatile("cp.async.bulk.tensor.2d.shared::cluster.global.mbarrier::complete_tx::bytes.L2::cache_hint [%0], [%1, {%3, %4}], [%2], %5;"
               ::"r"(dst), "l"(m), "r"(bar), "r"(c0), "r"(c1), "l"(l2_stream()) : "memory");
}
__device__ __forceinline__ void bulk_load(uint32_t dst, const void* src, uint32_t bytes, uint32_t bar) {
  asm volatile("cp.async.bulk.shared::cluster.global.mbarrier::complete_tx::bytes [%0], [%1], %2, [%3];" ::"r"(dst), "l"(src), "r"(bytes), "r"(bar) : "memory");
}
__device__ __forceinline__ void bulk_load_stream(uint32_t dst, const void* src, uint32_t bytes, uint32_t bar, uint64_t pol = l2_stream()) {
  asm volatile("cp.async.bulk.shared::cluster.global.mbarrier::complete_tx::bytes.L2::cache_hint [%0], [%1], %2, [%3], %4;"
               ::"r"(dst), "l"(src), "r"(bytes), "r"(bar), "l"(pol) : "memory");
}
__device__ __forceinline__ void tma2d_store(const CUtensorMap* m, uint32_t src, int c0, int c1) {
  asm volatile("cp.async.bulk.tensor.2d.global.shared::cta.bulk_group [%0, {%2, %3}], [%1];" ::"l"(m), "r"(src), "r"(c0), "r"(c1) : "memory");
}
__device__ __forceinline__ void bulk_store(void* dst, uint32_t src, uint32_t bytes) {
  asm volatile("cp.async.bulk.global.shared::cta.bulk_group [%0], [%1], %2;" ::"l"(dst), "r"(src), "r"(bytes) : "memory");
}
__device__ __forceinline__ int slice_of(int i) { return i + ((i & 7) == 1) - ((i & 7) == 2); }
__device__ __forceinline__ uint32_t unit_of(uint32_t table, uint32_t i) { return ((table >> (i * 4)) & 15) * UNIT; }
__device__ __forceinline__ void tma3d(uint32_t dst, const CUtensorMap* m, int c0, int c1, int c2, uint32_t bar) {
  asm volatile("cp.async.bulk.tensor.3d.shared::cluster.global.mbarrier::complete_tx::bytes.L2::cache_hint [%0], [%1, {%3, %4, %5}], [%2], %6;"
               ::"r"(dst), "l"(m), "r"(bar), "r"(c0), "r"(c1), "r"(c2), "l"(l2_stream()) : "memory");
}
template <bool STREAM>
__device__ __forceinline__ void tma3d_mc(uint32_t dst, const CUtensorMap* m, int c0, int c1, int c2, uint32_t bar) {
  if (STREAM)
    asm volatile("cp.async.bulk.tensor.3d.shared::cluster.global.mbarrier::complete_tx::bytes.multicast::cluster.L2::cache_hint [%0], [%1, {%3, %4, %5}], [%2], %6, %7;"
                 ::"r"(dst), "l"(m), "r"(bar), "r"(c0), "r"(c1), "r"(c2), "h"((uint16_t)3), "l"(l2_stream()) : "memory");
  else
    asm volatile("cp.async.bulk.tensor.3d.shared::cluster.global.mbarrier::complete_tx::bytes.multicast::cluster [%0], [%1, {%3, %4, %5}], [%2], %6;"
                 ::"r"(dst), "l"(m), "r"(bar), "r"(c0), "r"(c1), "r"(c2), "h"((uint16_t)3) : "memory");
}
__device__ __forceinline__ void prefetch_map(const CUtensorMap* m) {
  asm volatile("prefetch.tensormap [%0];" ::"l"(m) : "memory");
}
__device__ __forceinline__ void fence_async() { asm volatile("fence.proxy.async.global;" ::: "memory"); }
__device__ __forceinline__ void fence_async_smem() { asm volatile("fence.proxy.async.shared::cta;" ::: "memory"); }
__device__ __forceinline__ void bar_sync(int id, int n) { asm volatile("bar.sync %0, %1;" ::"r"(id), "r"(n) : "memory"); }
__device__ __forceinline__ void bar_arrive(int id, int n) { asm volatile("bar.arrive %0, %1;" ::"r"(id), "r"(n) : "memory"); }
__device__ __forceinline__ void wg_fence() { asm volatile("wgmma.fence.sync.aligned;" ::: "memory"); }
__device__ __forceinline__ void wg_commit() { asm volatile("wgmma.commit_group.sync.aligned;" ::: "memory"); }
template <int N> __device__ __forceinline__ void wg_wait() { asm volatile("wgmma.wait_group.sync.aligned %0;" ::"n"(N) : "memory"); }
__device__ __forceinline__ uint64_t make_desc(uint32_t addr, uint32_t lbo, uint32_t sbo) {
  return (uint64_t)((addr & 0x3FFFF) >> 4) | ((uint64_t)(lbo >> 4) << 16) | ((uint64_t)(sbo >> 4) << 32) | (1ull << 62);
}
__device__ __forceinline__ uint32_t ld_relaxed(const uint32_t* p) {
  uint32_t v; asm volatile("ld.relaxed.gpu.global.u32 %0, [%1];" : "=r"(v) : "l"(p) : "memory"); return v;
}
__device__ __forceinline__ uint32_t ld_acquire(const uint32_t* p) {
  uint32_t v; asm volatile("ld.acquire.gpu.global.u32 %0, [%1];" : "=r"(v) : "l"(p) : "memory"); return v;
}
__device__ __forceinline__ uint4 ld_relaxed4(const uint32_t* p) {
  uint4 v; asm volatile("ld.relaxed.gpu.global.v4.u32 {%0,%1,%2,%3}, [%4];" : "=r"(v.x), "=r"(v.y), "=r"(v.z), "=r"(v.w) : "l"(p) : "memory"); return v;
}
__device__ __forceinline__ void st_relaxed(uint32_t* p, uint32_t v) {
  asm volatile("st.relaxed.gpu.global.u32 [%0], %1;" ::"l"(p), "r"(v) : "memory");
}
__device__ __forceinline__ void st_relaxed4(uint32_t* p, uint32_t a, uint32_t b, uint32_t c, uint32_t d) {
  asm volatile("st.relaxed.gpu.global.v4.u32 [%0], {%1,%2,%3,%4};" ::"l"(p), "r"(a), "r"(b), "r"(c), "r"(d) : "memory");
}
__device__ __forceinline__ void st_b128(uint32_t* p, uint32_t a, uint32_t b, uint32_t c, uint32_t d) {
  asm volatile("{ .reg .b64 u, v; .reg .b128 w; mov.b64 u, {%1, %2}; mov.b64 v, {%3, %4}; mov.b128 w, {u, v}; st.relaxed.gpu.global.b128 [%0], w; }"
               ::"l"(p), "r"(a), "r"(b), "r"(c), "r"(d) : "memory");
}
__device__ __forceinline__ uint4 ld_b128(const uint32_t* p) {
  uint4 r;
  asm volatile("{ .reg .b64 u, v; .reg .b128 w; ld.relaxed.gpu.global.b128 w, [%4]; mov.b128 {u, v}, w; mov.b64 {%0, %1}, u; mov.b64 {%2, %3}, v; }"
               : "=r"(r.x), "=r"(r.y), "=r"(r.z), "=r"(r.w) : "l"(p) : "memory");
  return r;
}
__device__ __forceinline__ void st_pairs(uint32_t* p, uint32_t a, uint32_t b, uint32_t tag) {
  asm volatile("{ .reg .b64 u, v; mov.b64 u, {%1, %3}; mov.b64 v, {%2, %3}; st.relaxed.gpu.global.v2.b64 [%0], {u, v}; }"
               ::"l"(p), "r"(a), "r"(b), "r"(tag) : "memory");
}
__device__ __forceinline__ uint4 ld_pairs(const uint32_t* p) {
  uint4 v;
  asm volatile("{ .reg .b64 u, v; ld.relaxed.gpu.global.v2.b64 {u, v}, [%4]; mov.b64 {%0, %1}, u; mov.b64 {%2, %3}, v; }"
               : "=r"(v.x), "=r"(v.y), "=r"(v.z), "=r"(v.w) : "l"(p) : "memory");
  return v;
}
__device__ __forceinline__ uint2 ld_pair(const uint32_t* p) {
  uint2 v;
  asm volatile("{ .reg .b64 u; ld.relaxed.gpu.global.b64 u, [%2]; mov.b64 {%0, %1}, u; }" : "=r"(v.x), "=r"(v.y) : "l"(p) : "memory");
  return v;
}
__device__ __forceinline__ void red_release(uint32_t* p, uint32_t v) {
  asm volatile("red.release.gpu.global.add.u32 [%0], %1;" ::"l"(p), "r"(v) : "memory");
}
__device__ __forceinline__ uint32_t ldg_nc1(const void* p) {
  uint32_t v;
  asm volatile("ld.global.nc.u32 %0, [%1];" : "=r"(v) : "l"(p));
  return v;
}
__device__ __forceinline__ uint4 ldg_nc4(const void* p) {
  uint4 v; asm volatile("ld.global.nc.L1::no_allocate.v4.u32 {%0,%1,%2,%3}, [%4];" : "=r"(v.x), "=r"(v.y), "=r"(v.z), "=r"(v.w) : "l"(p)); return v;
}
__device__ __forceinline__ uint4 ldg_stream4(const void* p) {
  uint4 v;
  asm volatile("ld.global.nc.L1::no_allocate.L2::cache_hint.v4.u32 {%0,%1,%2,%3}, [%4], %5;" : "=r"(v.x), "=r"(v.y), "=r"(v.z), "=r"(v.w) : "l"(p), "l"(l2_stream()));
  return v;
}
__device__ __forceinline__ void stg4(void* p, uint4 v) {
  asm volatile("st.global.v4.u32 [%0], {%1,%2,%3,%4};" ::"l"(p), "r"(v.x), "r"(v.y), "r"(v.z), "r"(v.w) : "memory");
}
__device__ __forceinline__ void wait_counter(const uint32_t* p, uint32_t target) {
  uint32_t n = 0;
  while (__any_sync(0xffffffffu, (int)(ld_acquire(p) - target) < 0)) { watchdog(n); }
}
__device__ __forceinline__ uint32_t tagf(float v, uint32_t tag) { return (__float_as_uint(v) & ~3u) | tag; }
__device__ __forceinline__ bool tag_ok(uint4 v, uint32_t tag) { return (((v.x ^ tag) | (v.y ^ tag) | (v.z ^ tag) | (v.w ^ tag)) & 3u) == 0; }
__device__ __forceinline__ float untag_sum(uint32_t a, uint32_t b) { return __uint_as_float(a & ~3u) + __uint_as_float(b & ~3u); }
__device__ __forceinline__ uint4 poll4(const uint32_t* p, uint32_t tag) {
  uint4 v = ld_relaxed4(p);
  uint32_t n = 0;
  while (!__all_sync(0xffffffffu, tag_ok(v, tag))) { v = ld_relaxed4(p); watchdog(n); }
  return v;
}
__device__ __forceinline__ float bf_lo(uint32_t v) { return __uint_as_float(v << 16); }
__device__ __forceinline__ float bf_hi(uint32_t v) { return __uint_as_float(v & 0xffff0000u); }
__device__ __forceinline__ uint32_t pack_bf(float lo, float hi) {
  uint32_t r; asm("cvt.rn.bf16x2.f32 %0, %1, %2;" : "=r"(r) : "f"(hi), "f"(lo)); return r;
}
__device__ __forceinline__ float rbf(float v) { return __uint_as_float(pack_bf(0.f, v) & 0xffff0000u); }
__device__ __forceinline__ uint32_t hmul2(uint32_t a, uint32_t b) {
  uint32_t r; asm("mul.rn.bf16x2 %0, %1, %2;" : "=r"(r) : "r"(a), "r"(b)); return r;
}
__device__ __forceinline__ uint32_t hadd2(uint32_t a, uint32_t b) {
  uint32_t r; asm("add.rn.bf16x2 %0, %1, %2;" : "=r"(r) : "r"(a), "r"(b)); return r;
}
__device__ __forceinline__ uint32_t hsub2(uint32_t a, uint32_t b) {
  uint32_t r; asm("sub.rn.bf16x2 %0, %1, %2;" : "=r"(r) : "r"(a), "r"(b)); return r;
}
__device__ __forceinline__ float rcp(float x) { float r; asm("rcp.approx.ftz.f32 %0, %1;" : "=f"(r) : "f"(x)); return r; }
__device__ __forceinline__ float ex2(float x) { float r; asm("ex2.approx.ftz.f32 %0, %1;" : "=f"(r) : "f"(x)); return r; }
__device__ __forceinline__ void stmatrix4(uint32_t addr, uint32_t a, uint32_t b, uint32_t c, uint32_t d) {
  asm volatile("stmatrix.sync.aligned.m8n8.x4.shared.b16 [%0], {%1,%2,%3,%4};" ::"r"(addr), "r"(a), "r"(b), "r"(c), "r"(d) : "memory");
}
__device__ __forceinline__ void ldmatrix4(uint32_t addr, uint32_t& a, uint32_t& b, uint32_t& c, uint32_t& d) {
  asm volatile("ldmatrix.sync.aligned.m8n8.x4.shared.b16 {%0,%1,%2,%3}, [%4];" : "=r"(a), "=r"(b), "=r"(c), "=r"(d) : "r"(addr) : "memory");
}
__device__ __forceinline__ void ldmatrix4t(uint32_t addr, uint32_t& a, uint32_t& b, uint32_t& c, uint32_t& d) {
  asm volatile("ldmatrix.sync.aligned.m8n8.x4.trans.shared.b16 {%0,%1,%2,%3}, [%4];" : "=r"(a), "=r"(b), "=r"(c), "=r"(d) : "r"(addr) : "memory");
}
__device__ __forceinline__ void mma16816(float (&d)[4], uint32_t a0, uint32_t a1, uint32_t a2, uint32_t a3, uint32_t b0, uint32_t b1) {
  asm volatile("mma.sync.aligned.m16n8k16.row.col.f32.bf16.bf16.f32 {%0,%1,%2,%3}, {%4,%5,%6,%7}, {%8,%9}, {%0,%1,%2,%3};"
               : "+f"(d[0]), "+f"(d[1]), "+f"(d[2]), "+f"(d[3]) : "r"(a0), "r"(a1), "r"(a2), "r"(a3), "r"(b0), "r"(b1));
}
__device__ __forceinline__ void sts1(uint32_t a, uint32_t v) { asm volatile("st.shared.u32 [%0], %1;" ::"r"(a), "r"(v) : "memory"); }
__device__ __forceinline__ uint4 lds4(uint32_t a) {
  uint4 v; asm volatile("ld.shared.v4.u32 {%0,%1,%2,%3}, [%4];" : "=r"(v.x), "=r"(v.y), "=r"(v.z), "=r"(v.w) : "r"(a) : "memory"); return v;
}
__device__ __forceinline__ uint2 lds2(uint32_t a) {
  uint2 v; asm volatile("ld.shared.v2.u32 {%0,%1}, [%2];" : "=r"(v.x), "=r"(v.y) : "r"(a) : "memory"); return v;
}
__device__ __forceinline__ uint32_t lds1(uint32_t a) {
  uint32_t v; asm volatile("ld.shared.u32 %0, [%1];" : "=r"(v) : "r"(a) : "memory"); return v;
}
__device__ __forceinline__ void sts2(uint32_t a, uint32_t x, uint32_t y) { asm volatile("st.shared.v2.u32 [%0], {%1,%2};" ::"r"(a), "r"(x), "r"(y) : "memory"); }
__device__ __forceinline__ void sts4(uint32_t a, uint4 v) {
  asm volatile("st.shared.v4.u32 [%0], {%1,%2,%3,%4};" ::"r"(a), "r"(v.x), "r"(v.y), "r"(v.z), "r"(v.w) : "memory");
}
__device__ __forceinline__ float silu_f(float v) { return __fdividef(v, 1.f + __expf(-v)); }
__device__ __forceinline__ uint32_t hfma2(uint32_t a, uint32_t b, uint32_t c) {
  uint32_t r; asm("fma.rn.bf16x2 %0, %1, %2, %3;" : "=r"(r) : "r"(a), "r"(b), "r"(c)); return r;
}
__device__ __forceinline__ void split_inv(float sd, uint32_t& ih, uint32_t& il) {
  const float inv = rcp(sd);
  ih = pack_bf(inv, inv);
  const float lo = inv - bf_lo(ih);
  il = pack_bf(lo, lo);
}
__device__ __forceinline__ uint32_t ln_norm(uint32_t x, uint32_t mean2, uint32_t ih, uint32_t il) {
  const uint32_t d = hsub2(x, mean2);
  return hfma2(d, ih, hmul2(d, il));
}
__device__ __forceinline__ uint32_t ln_mod(uint32_t x, uint32_t mean2, uint32_t ih, uint32_t il, uint32_t c1, uint32_t sh) {
  return hadd2(hmul2(ln_norm(x, mean2, ih, il), c1), sh);
}

#define R8(a, i) "+f"(a[i]), "+f"(a[i + 1]), "+f"(a[i + 2]), "+f"(a[i + 3]), "+f"(a[i + 4]), "+f"(a[i + 5]), "+f"(a[i + 6]), "+f"(a[i + 7])
#define D64 "{%0,%1,%2,%3,%4,%5,%6,%7,%8,%9,%10,%11,%12,%13,%14,%15,%16,%17,%18,%19,%20,%21,%22,%23,%24,%25,%26,%27,%28,%29,%30,%31," \
            "%32,%33,%34,%35,%36,%37,%38,%39,%40,%41,%42,%43,%44,%45,%46,%47,%48,%49,%50,%51,%52,%53,%54,%55,%56,%57,%58,%59,%60,%61,%62,%63}"
template <int TB>
__device__ __forceinline__ void mma_ss(float (&d)[64], uint64_t da, uint64_t db, int sc) {
  asm volatile("{\n.reg .pred p;\nsetp.ne.b32 p, %66, 0;\n"
               "wgmma.mma_async.sync.aligned.m64n128k16.f32.bf16.bf16 " D64 ", %64, %65, p, 1, 1, 0, %67;\n}"
               : R8(d, 0), R8(d, 8), R8(d, 16), R8(d, 24), R8(d, 32), R8(d, 40), R8(d, 48), R8(d, 56)
               : "l"(da), "l"(db), "r"(sc), "n"(TB));
}
template <int TB>
__device__ __forceinline__ void mma_rs(float (&d)[64], uint32_t a0, uint32_t a1, uint32_t a2, uint32_t a3, uint64_t db, int sc) {
  asm volatile("{\n.reg .pred p;\nsetp.ne.b32 p, %69, 0;\n"
               "wgmma.mma_async.sync.aligned.m64n128k16.f32.bf16.bf16 " D64 ", {%64,%65,%66,%67}, %68, p, 1, 1, %70;\n}"
               : R8(d, 0), R8(d, 8), R8(d, 16), R8(d, 24), R8(d, 32), R8(d, 40), R8(d, 48), R8(d, 56)
               : "r"(a0), "r"(a1), "r"(a2), "r"(a3), "l"(db), "r"(sc), "n"(TB));
}
#define D128 "{%0,%1,%2,%3,%4,%5,%6,%7,%8,%9,%10,%11,%12,%13,%14,%15,%16,%17,%18,%19,%20,%21,%22,%23,%24,%25,%26,%27,%28,%29,%30,%31," \
             "%32,%33,%34,%35,%36,%37,%38,%39,%40,%41,%42,%43,%44,%45,%46,%47,%48,%49,%50,%51,%52,%53,%54,%55,%56,%57,%58,%59,%60,%61,%62,%63," \
             "%64,%65,%66,%67,%68,%69,%70,%71,%72,%73,%74,%75,%76,%77,%78,%79,%80,%81,%82,%83,%84,%85,%86,%87,%88,%89,%90,%91,%92,%93,%94,%95," \
             "%96,%97,%98,%99,%100,%101,%102,%103,%104,%105,%106,%107,%108,%109,%110,%111,%112,%113,%114,%115,%116,%117,%118,%119,%120,%121,%122,%123,%124,%125,%126,%127}"
#define R128(d, e) R8(d, 0), R8(d, 8), R8(d, 16), R8(d, 24), R8(d, 32), R8(d, 40), R8(d, 48), R8(d, 56), \
                   R8(e, 0), R8(e, 8), R8(e, 16), R8(e, 24), R8(e, 32), R8(e, 40), R8(e, 48), R8(e, 56)
__device__ __forceinline__ void mma256_ss(float (&d)[64], float (&e)[64], uint64_t da, uint64_t db, int sc) {
  asm volatile("{\n.reg .pred p;\nsetp.ne.b32 p, %130, 0;\n"
               "wgmma.mma_async.sync.aligned.m64n256k16.f32.bf16.bf16 " D128 ", %128, %129, p, 1, 1, 0, 1;\n}"
               : R128(d, e) : "l"(da), "l"(db), "r"(sc));
}
__device__ __forceinline__ void mma256_rs(float (&d)[64], float (&e)[64], uint32_t a0, uint32_t a1, uint32_t a2, uint32_t a3, uint64_t db) {
  asm volatile("{\n.reg .pred p;\nsetp.ne.b32 p, 1, 0;\n"
               "wgmma.mma_async.sync.aligned.m64n256k16.f32.bf16.bf16 " D128 ", {%128,%129,%130,%131}, %132, p, 1, 1, 1;\n}"
               : R128(d, e) : "r"(a0), "r"(a1), "r"(a2), "r"(a3), "l"(db));
}
template <int N> __device__ __forceinline__ void keep(float (&a)[N]) {
#pragma unroll
  for (int i = 0; i < N; i++) asm volatile("" : "+f"(a[i])::"memory");
}
template <int N> __device__ __forceinline__ void keep(uint32_t (&a)[N]) {
#pragma unroll
  for (int i = 0; i < N; i++) asm volatile("" : "+r"(a[i])::"memory");
}

#define STAMP(idx) do {} while (0)
#define PROF(grp, cond, idx) do {} while (0)

constexpr float SCL2 = 1.4426950408889634f * 0.08838834764831845f;

__device__ __forceinline__ void pack_p(const float (&s)[64], uint32_t (&p)[32]) {
#pragma unroll
  for (int i = 0; i < 32; i++) p[i] = pack_bf(s[2 * i], s[2 * i + 1]);
}

__device__ __forceinline__ void issue_qk(float (&s)[64], uint32_t q0, uint32_t q1, uint32_t kslot) {
  const uint64_t db = make_desc(kslot, 16, 1024), da0 = make_desc(q0, 16, 1024), da1 = make_desc(q1, 16, 1024);
#pragma unroll
  for (int kk = 0; kk < 8; kk++) mma_ss<0>(s, (kk < 4 ? da0 : da1) + (kk & 3) * 2, db + (kk >> 2) * 1024 + (kk & 3) * 2, kk != 0);
}
__device__ __forceinline__ void issue_pv(float (&o)[64], uint32_t (&p)[32], uint32_t vslot, int acc) {
  uint64_t db = make_desc(vslot, 16384, 1024);
#pragma unroll
  for (int kk = 0; kk < 8; kk++)
    mma_rs<1>(o, p[4 * kk], p[4 * kk + 1], p[4 * kk + 2], p[4 * kk + 3], db + kk * 128, kk == 0 ? acc : 1);
}

template <int H>
__device__ __forceinline__ void store_chunk(const float (&a)[64], uint32_t addr) {
#pragma unroll
  for (int i = 8 * H; i < 8 * H + 8; i += 2)
    stmatrix4(addr ^ ((i & 7) << 4), pack_bf(a[4 * i], a[4 * i + 1]), pack_bf(a[4 * i + 2], a[4 * i + 3]),
              pack_bf(a[4 * i + 4], a[4 * i + 5]), pack_bf(a[4 * i + 6], a[4 * i + 7]));
}
template <int H>
__device__ __forceinline__ void store_chunk(const float (&a)[64], float i0, float i1, uint32_t addr) {
#pragma unroll
  for (int i = 8 * H; i < 8 * H + 8; i += 2)
    stmatrix4(addr ^ ((i & 7) << 4), pack_bf(a[4 * i] * i0, a[4 * i + 1] * i0), pack_bf(a[4 * i + 2] * i1, a[4 * i + 3] * i1),
              pack_bf(a[4 * i + 4] * i0, a[4 * i + 5] * i0), pack_bf(a[4 * i + 6] * i1, a[4 * i + 7] * i1));
}
__device__ __forceinline__ float inv_quad_sum(float l) {
  l += __shfl_xor_sync(0xffffffffu, l, 1);
  l += __shfl_xor_sync(0xffffffffu, l, 2);
  return rcp(l);
}

__device__ __forceinline__ void write_table(uint32_t table, bool ca, uint32_t t, const uint4& m0, const uint4& m1) {
  float c0 = untag_sum(m0.x, m1.x), c1 = untag_sum(m0.y, m1.y), c2 = untag_sum(m0.z, m1.z), c3 = untag_sum(m0.w, m1.w);
  if (ca) { c0 = 1.f + rbf(c0); c1 = 1.f + rbf(c1); c2 = 1.f + rbf(c2); c3 = 1.f + rbf(c3); }
  const uint32_t d = table + (t >> 2) * 64 + (t & 1) * 32 + (t & 2) * 2 + (ca ? 0 : 8);
  sts1(d, pack_bf(c0, c1));
  sts1(d + 16, pack_bf(c2, c3));
}

__device__ __forceinline__ void ln_scalars(float mean, float var, float& mb, float& sd) {
  mb = rbf(mean);
  float r; asm("sqrt.approx.ftz.f32 %0, %1;" : "=f"(r) : "f"(rbf(rbf(var) + 1e-5f)));
  sd = rbf(r);
}

__global__ void __cluster_dims__(2, 1, 1) __launch_bounds__(384, 1) fused_kernel(const __grid_constant__ Maps maps, const Ptrs P) {
  extern __shared__ __align__(1024) uint8_t smem_raw[];
  const uint32_t base = smem_u32(smem_raw);
  const int tid = threadIdx.x, lane = tid & 31;
  const int warp = __shfl_sync(0xffffffffu, tid >> 5, 0);
  int b = blockIdx.x;
  if (b < NMAIN) {
    const int p = b >> 1;
    const int grp = p < 4 ? 7 : (p < 36 ? (p + 2) & 7 : (p - 30) % 7), k = p < 4 ? 4 + p : (p < 36 ? (p - 4) >> 3 : 4 + (p - 36) / 7);
    b = grp << 4 | k << 1 | (b & 1);
  }
  PROF(31, tid == 0, 0);

  if (b >= NMAIN) {
    float* sc = reinterpret_cast<float*>(smem_raw);
    float* red = sc + DM;
    for (int k = tid; k < DM; k += 384) sc[k] = rbf(silu_f(__bfloat162float(P.c[k])));
    __syncthreads();
    if (tid < 256) {
      const int col = 2048 + (b - NMAIN) * 1024 + (tid & 127) * 8, r0 = (tid >> 7) * 512;
      float acc[8];
#pragma unroll
      for (int e = 0; e < 8; e++) acc[e] = 0.f;
#pragma unroll 1
      for (int r = r0; r < r0 + 512; r += HU) {
        uint4 w[HU];
#pragma unroll
        for (int u = 0; u < HU; u++) w[u] = ldg_stream4(P.w_mod + (size_t)(r + u) * NMOD + col);
#pragma unroll
        for (int u = 0; u < HU; u++) {
          float s = sc[r + u];
          acc[0] += s * bf_lo(w[u].x); acc[1] += s * bf_hi(w[u].x); acc[2] += s * bf_lo(w[u].y); acc[3] += s * bf_hi(w[u].y);
          acc[4] += s * bf_lo(w[u].z); acc[5] += s * bf_hi(w[u].z); acc[6] += s * bf_lo(w[u].w); acc[7] += s * bf_hi(w[u].w);
        }
      }
      if (tid >= 128) {
#pragma unroll
        for (int e = 0; e < 8; e++) red[(tid & 127) * 8 + e] = acc[e];
      }
      const uint32_t tag = ld_relaxed(&g_epoch) % 3 + 1;
      bar_sync(1, 256);
      if (tid < 128) {
        uint32_t o[8];
#pragma unroll
        for (int e = 0; e < 8; e++) o[e] = __float_as_uint(rbf(acc[e] + red[tid * 8 + e])) | tag;
        st_relaxed4(g_mod + col, o[0], o[1], o[2], o[3]);
        st_relaxed4(g_mod + col + 4, o[4], o[5], o[6], o[7]);
        const uint4 wr = ldg_nc4(P.w_r + tid * 8);
        const uint32_t wv[4] = {wr.x, wr.y, wr.z, wr.w};
        float dsum = 0.f;
#pragma unroll
        for (int e = 0; e < 8; e++) {
          const float m = bf_hi(o[e]);
          dsum += (b == NMAIN + 2 ? rbf(1.f + m) : m) * ((e & 1) ? bf_hi(wv[e >> 1]) : bf_lo(wv[e >> 1]));
        }
#pragma unroll
        for (int k = 16; k > 0; k >>= 1) dsum += __shfl_xor_sync(0xffffffffu, dsum, k);
        if (lane == 0) st_relaxed(g_mod + (b - NMAIN) * 4 + warp, tagf(dsum, tag));
      }
    }
    PROF(2, tid == 0, 1);
    return;
  }

  const int rank = b & 1;
  const int rb = ((b >> 4) << 1) | rank, cj = (b >> 1) & 7;
  const bool late = b & 4;
  const uint32_t bfull = base + OFF_BAR, bempty = bfull + NSLOT * 8;
  const uint32_t gfull = bempty + NSLOT * 8, gempty = gfull + 32;
  const uint32_t bar_ofull = gempty + 32;
  const uint32_t bar_ofree = bar_ofull + 32;
  const uint32_t bar_par = bar_ofree + 32;
  const uint32_t bar_mod = bar_par + 8;
  const uint32_t bar_pread = bar_mod + 8;
  const uint32_t bar_xres = bar_pread + 8;
  const uint32_t bar_ring = bar_xres + 8;
  const uint32_t bar_box = bar_ring + 24;
  const uint32_t bar_go = bar_box + 96;
  const uint32_t bar_go2 = bar_go + 16;
  const uint32_t bar_cnt = bar_go + 24;
  const uint32_t xfull = bar_go + 40, xempty = xfull + 32;
  const uint32_t bar_hw = xempty + 32, bar_hx = bar_hw + 8;
  const uint32_t bar_hpub = bar_hx + 16;
  const uint32_t bar_win = bar_hpub + 16;
  const uint32_t bar_rx = bar_win + 8;
  const uint32_t bar_sel = bar_rx + 8;
  const uint32_t bar_gate = bar_sel + 8;
  const uint32_t bar_rel = bar_gate + 8;
  const uint32_t bar_od = bar_rel + 8;
  const uint32_t bar_mod2 = bar_od + 8;
  const uint32_t bar_res = bar_go + 8;
  const uint32_t stage = base + OFF_STAGE, par = base + OFF_PAR;

  if (warp == 10 && elect_one()) prefetch_map(&maps.wm);
  if (warp == 8 && elect_one()) {
    for (int s = 0; s < NSLOT; s++) { mbar_init(bfull + s * 8, 1); mbar_init(bempty + s * 8, 16); }
    for (int s = 0; s < 4; s++) { mbar_init(gfull + s * 8, 1); mbar_init(gempty + s * 8, 16); mbar_init(xfull + s * 8, 1); mbar_init(xempty + s * 8, 8); mbar_init(bar_ofree + s * 8, 1); mbar_init(bar_ofull + s * 8, 128); }
    mbar_init(bar_par, 64); mbar_init(bar_mod, 256); mbar_init(bar_pread, 2); mbar_init(bar_xres, 1);
    mbar_init(bar_ring, 8); mbar_init(bar_ring + 8, 8); mbar_init(bar_ring + 16, 8);
    mbar_init(bar_go, 1); mbar_init(bar_go2, 1); mbar_init(bar_cnt, 1); mbar_init(bar_cnt + 8, 1); mbar_init(bar_hpub, 8); mbar_init(bar_hpub + 8, 8); mbar_init(bar_res, 1); mbar_init(bar_win, 1); mbar_init(bar_rx, 1); mbar_init(bar_sel, 64); mbar_init(bar_gate, 8); mbar_init(bar_rel, 8); mbar_init(bar_od, 1); mbar_init(bar_mod2, 64);
    for (int s = 0; s < 12; s++) mbar_init(bar_box + s * 8, 1);
    asm volatile("fence.mbarrier_init.release.cluster;" ::: "memory");
    prefetch_map(&maps.x); prefetch_map(&maps.wq); prefetch_map(&maps.k); prefetch_map(&maps.v);
  }
  if (warp == 9 && elect_one()) {
    mbar_init(bar_hw, 1); mbar_init(bar_hx, 1); mbar_init(bar_hx + 8, 1);
    asm volatile("fence.mbarrier_init.release.cluster;" ::: "memory");
    mbar_expect_tx(bar_hw, 32768);
    mbar_expect_tx(bar_hx, 16384);
    mbar_expect_tx(bar_hx + 8, 16384);
    const __nv_bfloat16* xs = P.x + (size_t)(rb * 128 + cj * 16) * DM;
    bulk_load(base + 2 * GST_BYTES, xs, 16384, bar_hx);
    if (!late) {
      tma2d(stage, &maps.wm, (b >> 1) * 32, rank * 512, bar_hw);
      tma2d(stage + 16384, &maps.wm, (b >> 1) * 32, rank * 512 + 256, bar_hw);
    }
    bulk_load(base + 3 * GST_BYTES, xs + 8 * DM, 16384, bar_hx + 8);
  }
  cluster_arrive();

  if (warp >= 8) {
    asm volatile("setmaxnreg.dec.sync.aligned.u32 40;");
    if (warp < 10) bar_arrive(1, 320);
    const uint32_t epoch = ld_relaxed(&g_epoch);
    cluster_wait();
    if (warp == 8) {
      const int kvrow = (cj >> 1) * SK + (SK - WIN);
      int wch = cj * 8 + rank * 2;
#pragma unroll 1
      for (int ps = 0; ps < 3; ps++) {
        const CUtensorMap* mw = ps == 2 ? &maps.wo : &maps.wq;
        const uint32_t xt = ps == 1 ? XT1 : XT2, wt = ps == 0 ? WT0 : (ps == 1 ? WT1 : WT2);
        const int nst = ps == 2 ? 32 : 16;
#pragma unroll 1
        for (int i = 0; i < nst; i++) {
          const uint32_t bf = gfull + (i & 3) * 8;
          const int kt = ps == 2 ? (((cj & 1) * 4 + ((i >> 1) & 3)) * 4 + (i >> 3)) * 2 + (i & 1) : (ps ? i : slice_of(i) + (b & 14)) & 15;
          const uint32_t wd = base + unit_of(wt, i & 3) + rank * UNIT, xd = base + unit_of(xt, i & 3);
          const uint8_t* xs = g_act + (uint32_t)(rb * 80 + (ps - 1) * 16 + kt) * UNIT;
          if (ps == 0 && i == HD) mbar_wait(bar_mod, 0);
          if (ps == 2 && (i & 7) == 0 && i != 8) mbar_wait(i ? bar_cnt + i - 16 : bar_ofree + 24, 0);
          if ((i & 7) == 0) fence_async();
          if (i == RES0) mbar_wait(bar_res, 0);
          mbar_wait(bf, ((i >> 2) & 1) ^ 1);
          if (elect_one()) {
            mbar_expect_tx(bf, ps ? GST_BYTES : 2 * UNIT);
            if (ps && i < 2) bulk_load_stream(xd, xs, UNIT, bf);
            mbar_arrive_pred(bar_go, i == GOST);
            mbar_arrive_pred(bar_go2, ps == 1 && i == PG0);
            mbar_arrive_pred(bar_od, ps && i == (ps == 1 ? ODS1 : ODS) + 1);
            if (i == RES0) mbar_expect_tx(bar_xres, 32768);
          }
          const int wk = (i == 31 ? kt ^ (rank * 32) : kt) * 64, wc = i == 31 ? cj * 2 : wch;
          const uint64_t xp = i == 31 ? l2_normal() : l2_stream();
          mbar_wait(ps && i < 4 ? bempty + i * 8 : gempty + (i & 3) * 8, ((i >> 2) & 1) ^ 1);
          if (elect_one()) {
            tma3d_mc<true>(wd, mw, 0, wk, wc, bf);
            if (ps && i > 2) bulk_load_stream(xd, xs, UNIT, bf, xp);
            if (i == RES0 || i == RES1) tma2d(base + OFF_RES + (i == RES1) * UNIT, &maps.x, cj * 128 + (i == RES1) * 64, rb * 128, bar_xres);
          }
          if (ps && i == 2) {
            mbar_wait(bar_ofree + (ps - 1) * 16, 0);
            if (elect_one()) bulk_load_stream(xd, xs, UNIT, bf);
          }
        }
        if (ps == 2) break;
        wch = ps ? ((wch >> 3) ^ rank) * 2 : wch + 4;
#pragma unroll 1
        for (int u = 0; u < 16; u++) {
          const bool isk = (u == 0) || ((u & 1) && u < 15), kept = (0x1680 >> u) & 1;
          const int blk = (0x472FAD84u >> (u * 2)) & 3;
          const uint32_t sl = base + unit_of(ps ? AT1 : AT0, u & 3) + rank * UNIT, bf = bfull + (u & 3) * 8;
          mbar_wait(bf, ((u >> 2) & 1) ^ 1);
          if (!kept && elect_one()) mbar_expect_tx(bf, SLOT_BYTES);
          mbar_wait(u < 4 ? gempty + ((u + 1) >> 1) * 8 : bempty + (u & 3) * 8, ((u >> 2) & 1) ^ 1);
          if (elect_one()) {
            if (kept) mbar_arrive(bf);
            else if (ps && (blk >= 2 || u > 8)) tma3d_mc<true>(sl, isk ? &maps.k : &maps.v, 0, kvrow + blk * 128, rank, bf);
            else tma3d_mc<false>(sl, isk ? &maps.k : &maps.v, 0, kvrow + blk * 128, rank, bf);
          }
        }
      }
      if (elect_one()) mbar_expect_tx(bar_rx, UNIT);
      mbar_wait(bar_rel, 0);
      if (elect_one()) {
        bulk_load_stream(base + UNIT, g_act + (uint32_t)(rb * 80 + 16 + 63 - (cj & 1) * 32) * UNIT, UNIT, bar_rx);
      }
      if (b < NFFN) {
#pragma unroll 1
        for (int u = 0; u < 12; u++) {
          const uint32_t dst = base + unit_of(u < 4 ? FT_G : (u < 8 ? FT_U : FT_D), u & 3);
          if (elect_one()) mbar_expect_tx(bar_box + u * 8, UNIT);
          if (u == 0 || u == 2 || u == 8) mbar_wait(bar_ring + (u == 8 ? 16 : u * 4), 0);
          const int fp = u < 8 ? FPACE0 : FPACE;
          if (u >= fp) mbar_wait(bar_box + (u - fp) * 8, 0);
          if (elect_one()) {
            if (u < 8) tma2d(dst, u < 4 ? &maps.wg : &maps.wu, b * 32, (u & 3) * 256, bar_box + u * 8);
            else tma3d(dst, &maps.wd, 0, b * 32, (u - 8) * 4, bar_box + u * 8);
          }
        }
      }
    } else if (warp == 9) {
      const uint32_t target = 8 * (epoch + 1);
      uint32_t hmask = 0;
#pragma unroll 1
      for (int i = 0; i < 16; i++) {
        if (i == HDX) mbar_wait(bar_mod, 0);
        const int kt = (2 * cj + slice_of(i)) & 15;
        const uint32_t need = i == 15 ? 0xffffu : 1u << kt;
        if (i >= NRS && (hmask & need) != need) {
          uint32_t n = 0;
          do { hmask = __ballot_sync(0xffffffffu, ld_acquire(&g_cnt_h[rb * 32 + (lane & 15)]) == epoch + 1); watchdog(n); } while ((hmask & need) != need);
          PROF(1, lane == 0 && i == NRS, 26);
          fence_async();
        }
        mbar_wait(xempty + (i & 3) * 8, ((i >> 2) & 1) ^ 1);
        if (elect_one()) {
          mbar_expect_tx(xfull + (i & 3) * 8, UNIT);
          if (i < NRS) tma2d(base + (i & 3) * GST_BYTES, &maps.x, kt * 64, rb * 128, xfull + (i & 3) * 8);
          else bulk_load_stream(base + (i & 3) * GST_BYTES, g_act + (uint32_t)(rb * 80 + kt) * UNIT, UNIT, xfull + (i & 3) * 8);
        }
      }
      prefetch_map(&maps.wo);
#pragma unroll 1
      for (int t = 0; t < 4; t++) {
        if (t & 1) mbar_wait(bar_od, t >> 1);
        const int ops = OPS >> (t & 1);
#pragma unroll 1
        for (int p = 0; p < 32768; p += ops) {
          const uint32_t w = p >> 14, c = (p >> 13) & 1, off = w * 8192 + (p & 8191);
          mbar_wait(bar_ofull + (t & 1) * 16 + w * 8, t >> 1);
          if (elect_one()) {
            bulk_store(g_act + (uint32_t)(rb * 80 + 16 + (cj * 4 + t) * 2 + c) * UNIT + off, base + unit_of(QT, 2 * t + c) + off, ops);
            asm volatile("cp.async.bulk.commit_group;" ::: "memory");
            asm volatile("cp.async.bulk.wait_group.read 0;" ::: "memory");
          }
        }
        if (elect_one()) {
          mbar_arrive(t < 3 ? bar_ofree + t * 8 : bar_res);
          asm volatile("cp.async.bulk.wait_group 0;" ::: "memory");
          fence_async();
          red_release(&g_cnt_o[((rb * 4 + t) * 2 + (cj >> 2)) * 32], 2);
        }
        if (t) {
          wait_counter(&g_cnt_o[(rb * 8 + 2 * t + (cj & 1)) * 32], target);
          if (t & 1) wait_counter(&g_cnt_o[(rb * 8 + (t == 1 ? cj & 1 : 7 - (cj & 1))) * 32], target);
          if (elect_one()) mbar_arrive(t == 1 ? bar_ofree + 24 : bar_cnt + t * 8 - 16);
        }
      }
      PROF(2, lane == 0, 27);
      const uint32_t tag = epoch % 3 + 1;
      const uint32_t* inbox = g_cand + (b >> 4) % CR * 512 + (lane & 15) * CS;
      mbar_wait(bar_ring + 16, 0);
      uint32_t c0 = ld_relaxed(inbox), n = 0;
#define CAND_STEP(cv)                                                                                        \
      {                                                                                                      \
        const bool valid = (cv & 3u) == tag, all = __all_sync(0xffffffffu, valid);                           \
        const uint32_t best = __reduce_max_sync(0xffffffffu, valid ? cv : 0u);                               \
        const uint32_t blk = __ffs(__ballot_sync(0xffffffffu, cv == best)) - 1;                              \
        if (best) sts2(par + PAR_CONST + 56, best, (blk << 7 | (~best >> 2 & 127)) | (all ? 0x1800 : 0x800)); \
        if (all) break;                                                                                      \
        cv = ld_relaxed(inbox);                                                                              \
      }
      while (true) { CAND_STEP(c0) watchdog(n); }
    } else {
      const int t2 = tid - 320;
      if (late && warp == 10) {
        mbar_wait(bar_hx, 0);
        if (elect_one()) {
          tma2d(stage, &maps.wm, (b >> 1) * 32, rank * 512, bar_hw);
          tma2d(stage + 16384, &maps.wm, (b >> 1) * 32, rank * 512 + 256, bar_hw);
        }
      }
      {
        const uint32_t tag = epoch % 3 + 1;
        mbar_wait(bar_hx + 8, 0);
        mbar_wait(bar_hw, 0);
        __nanosleep(late ? OSL2 : OSL);
        {
          const uint32_t t7 = (warp & 1) * 64 + (lane >> 4) * 32 + 16 + (lane & 15);
          const uint32_t* pm = g_modp + ((cj * 128 + t7 * 4) & (DM - 1));
          uint4 m0, m1, m2, m3;
          uint32_t n = 0;
          do {
            m0 = ld_relaxed4(pm); m1 = ld_relaxed4(pm + 2 * DM); m2 = ld_relaxed4(pm + DM); m3 = ld_relaxed4(pm + 3 * DM);
            watchdog(n);
          } while (!__all_sync(0xffffffffu, tag_ok(m0, tag) && tag_ok(m1, tag) && tag_ok(m2, tag) && tag_ok(m3, tag)));
          write_table(par, false, t7, m0, m1);
          write_table(par, true, t7, m2, m3);
          mbar_arrive(bar_mod2);
        }
      }
      mbar_wait(bar_hpub + (warp & 1) * 8, 0);
      PROF(1, t2 == 0, 24);
#pragma unroll 1
      for (int c = 0; c < 8; c++) {
        const uint32_t off = (warp & 1) * UNIT + c * 2048 + lane * 16;
        uint8_t* dst = g_act + (uint32_t)(rb * 80 + cj * 2) * UNIT + off;
        const uint4 v0 = lds4(stage + off), v1 = lds4(stage + off + 512), v2 = lds4(stage + off + 1024), v3 = lds4(stage + off + 1536);
        stg4(dst, v0); stg4(dst + 512, v1); stg4(dst + 1024, v2); stg4(dst + 1536, v3);
      }
      __syncwarp();
      PROF(1, t2 == 0, 15);
      if (lane == 0) {
        mbar_arrive(bar_pread);
        red_release(&g_cnt_h[rb * 32 + cj * 2 + (warp & 1)], 1);
        PROF(1, t2 == 0, 25);
        prefetch_map(&maps.wg); prefetch_map(&maps.wu); prefetch_map(&maps.wd); prefetch_map(&maps.out);
      }
      __syncwarp();
      if (b < NFFN) {
        mbar_wait(bar_go2, 0);
        const __nv_bfloat16* pg = ((b & 1) ? P.w_up : P.w_gate) + (b >> 1) * 64 + (size_t)t2 * FF;
        const __nv_bfloat16* pd = P.w_down + (size_t)b * 32768 + t2 * 64;
        PROF(2, t2 == 0, 13);
#pragma unroll 1
        for (int i = 0; i < WN; i += WB) {
          uint32_t v[WB];
#pragma unroll
          for (int u = 0; u < WB; u++) {
            const int k = i + u;
            asm volatile("ld.global.cg.L2::128B.u32 %0, [%1];" : "=r"(v[u]) : "l"(k < 16 ? pg + (size_t)k * 64 * FF : pd + (k - 16) * 4096));
          }
#pragma unroll
          for (int u = 1; u < WB; u++) v[0] ^= v[u];
          sts1(par + PAR_SINK + t2 * 4, v[0]);
        }
        PROF(2, t2 == 0, 14);
      }
      const uint32_t tag = epoch % 3 + 1;
      mbar_wait(bar_go, 0);
      bar_sync(4, 64);
      if (warp == 10) {
        const uint32_t* src = g_mod + 2 * DM + cj * 128 + lane * 4;
        const uint2 wr = *reinterpret_cast<const uint2*>(P.w_r + cj * 128 + lane * 4);
        uint4 vga, vsb, vcb, vgb;
        uint32_t n = 0;
        do {
          vga = ld_relaxed4(src); vsb = ld_relaxed4(src + DM); vcb = ld_relaxed4(src + 2 * DM); vgb = ld_relaxed4(src + 3 * DM);
          watchdog(n);
        } while (!__all_sync(0xffffffffu, tag_ok(vga, tag) && tag_ok(vsb, tag) && tag_ok(vcb, tag) && tag_ok(vgb, tag)));
        const float c0 = rbf(1.f + bf_hi(vcb.x)), c1 = rbf(1.f + bf_hi(vcb.y)), c2 = rbf(1.f + bf_hi(vcb.z)), c3 = rbf(1.f + bf_hi(vcb.w));
        const float a0 = c0 * bf_lo(wr.x), a1 = c1 * bf_hi(wr.x), a2 = c2 * bf_lo(wr.y), a3 = c3 * bf_hi(wr.y);
        const uint32_t h0 = pack_bf(a0, a1), h1 = pack_bf(a2, a3);
        const uint32_t t1 = par + PAR_T1 + (lane >> 2) * 64 + (lane & 1) * 32 + (lane & 2) * 2;
        sts1(t1, h0); sts1(t1 + 8, pack_bf(a0 - bf_lo(h0), a1 - bf_hi(h0)));
        sts1(t1 + 16, h1); sts1(t1 + 24, pack_bf(a2 - bf_lo(h1), a3 - bf_hi(h1)));
        const uint32_t tg = par + PAR_SINK + (lane >> 3) * 64 + (lane & 1) * 32 + (lane & 6) * 2;
        sts1(tg, __byte_perm(vga.x, vga.y, 0x7632)); sts1(tg + 16, __byte_perm(vga.z, vga.w, 0x7632));
        sts4(par + PAR_T2 + lane * 32, make_uint4(pack_bf(c0, c1), __byte_perm(vsb.x, vsb.y, 0x7632), __byte_perm(vgb.x, vgb.y, 0x7632), __byte_perm(vga.x, vga.y, 0x7632)));
        sts4(par + PAR_T2 + lane * 32 + 16, make_uint4(pack_bf(c2, c3), __byte_perm(vsb.z, vsb.w, 0x7632), __byte_perm(vgb.z, vgb.w, 0x7632), __byte_perm(vga.z, vga.w, 0x7632)));
      } else {
        const uint4 g = poll4((lane & 8) ? g_mod + 8 - (lane & 1) * 4 : g_mod + 5 * DM + (b >> 4) * 128 + (lane & 7) * 16 + (b & 12), tag);
        sts1(par + PAR_CONST + 60, 0);
        if (lane < 8) sts1(par + PAR_CONST + 16 + lane * 4, (b & 2) ? ((b & 1) ? g.w : g.z) : ((b & 1) ? g.y : g.x));
        else if (lane < 10) sts2(par + PAR_CONST + (lane - 8) * 8, __float_as_uint(untag_sum(g.x, g.y) + untag_sum(g.z, g.w)), epoch);
      }
      __syncwarp();
#pragma unroll 1
      for (int q = 0; q < 32; q++) {
        st_b128(g_xch + ((size_t)b * 8 * 256 + q * 64 + t2) * 4, (epoch & 1) << 16, 0, 0, 0);
        __nanosleep(RSL);
      }
      for (int q = 0; q < 2; q++) st_relaxed4(g_stats + (((rb * 8 + q * 4 + (t2 >> 4)) * 8 + cj) * 16 + (t2 & 15)) * 4, 0, 0, 0, 0);
      if (b < NFFN)
        for (int q = 0; q < 2; q++) st_relaxed4(ypart_slot(b, q * 64 + t2), 0, 0, 0, 0);
      st_relaxed4(g_row + rb * 2 * DM + (t2 >> 5) * DM + cj * 128 + (t2 & 31) * 4, 0, 0, 0, 0);
      __threadfence();
      mbar_arrive(bar_par);
      mbar_wait(bar_gate, 0);
      uint32_t have = 0, n = 0;
      while (true) {
        const uint32_t st = lds1(par + PAR_CONST + 60) >> 7;
        if ((st & 31) != have) {
          const uint32_t* hsrc = g_row + (st & 15) * 2 * DM + t2 * 4;
          uint4 hv[4];
          bool ok = true;
#pragma unroll
          for (int i = 0; i < 4; i++) hv[i] = ld_pairs(hsrc + i * 256);
#pragma unroll
          for (int i = 0; i < 4; i++) {
            sts2(base + ((FT_G >> i * 4) & 15) * UNIT + (warp & 1) * 8192 + 256 + lane * 8, hv[i].x, hv[i].z);
            ok = ok && hv[i].y == tag && hv[i].w == tag;
          }
          have = __all_sync(0xffffffffu, ok) ? st & 31 : 0;
        }
        if ((st ^ have) == 32) break;
        watchdog(n);
      }
      mbar_arrive(bar_sel);
    }
    __syncwarp();
    cluster_arrive();
    {
      const uint32_t tag = epoch % 3 + 1, t3 = tid - 256;
      mbar_wait(bar_win, 0);
      uint2 win = lds2(par + PAR_CONST + 56);
      win.y &= 0x7ff;
      const uint32_t* fsrc = g_row + (win.y >> 7) * 2 * DM + (b >> 4) * 128 + (t3 & 7) * 16 + (b & 6) * 2 + ((b >> 2) & 2);
      const uint32_t* ysrc = ypart_slot(min(t3, NFFN - 1), b);
      uint2 fh = ld_pair(fsrc), fx = ld_pair(fsrc + DM);
      uint4 ya = ld_b128(ysrc);
      const float rwin = __uint_as_float(((int)win.x < 0 ? win.x & 0x7fffffffu : ~win.x) & ~0x1ffu);
      const float rs = rbf(rcp(1.f + __expf(-rbf(rwin))));
      uint32_t n = 0;
      while (__any_sync(0xffffffffu, fh.y != tag || fx.y != tag)) { fh = ld_pair(fsrc); fx = ld_pair(fsrc + DM); watchdog(n); }
      while (true) {
        const bool miss = ((ya.x & 1) | (ya.y & 1) << 1) != tag;
        if (!__any_sync(0xffffffffu, miss)) break;
        if (miss) ya = ld_b128(ysrc);
        watchdog(n);
      }
      PROF(8, t3 == 0, 5);
      float y[8] = {bf_lo(ya.x & ~1u), bf_hi(ya.x), bf_lo(ya.y & ~1u), bf_hi(ya.y), bf_lo(ya.z), bf_hi(ya.z), bf_lo(ya.w), bf_hi(ya.w)};
#pragma unroll
      for (int h = 4; h > 0; h >>= 1) {
        const bool up = lane & (h * 2);
#pragma unroll
        for (int e = 0; e < h; e++) y[e] = (up ? y[e + h] : y[e]) + __shfl_xor_sync(0xffffffffu, up ? y[e] : y[e + h], h * 2);
      }
      y[0] += __shfl_xor_sync(0xffffffffu, y[0], 1);
      if (!(lane & 1)) sts1(par + PAR_RED + 64 + t3 * 2, __float_as_uint(y[0]));
      bar_sync(4, 128);
      if (t3 < 8) {
        float y0 = 0.f;
#pragma unroll
        for (int w7 = 0; w7 < 7; w7++) y0 += __uint_as_float(lds1(par + PAR_RED + 64 + w7 * 32 + t3 * 4));
        const uint32_t gv = lds1(par + PAR_CONST + 16 + t3 * 4);
        const uint32_t upd = hmul2(pack_bf(y0, y0), pack_bf(rs, rs));
        const uint32_t r = hadd2(fx.x, hmul2(__byte_perm(gv, gv, 0x3232), hadd2(fh.x, upd)));
        reinterpret_cast<uint16_t*>(P.out)[(size_t)win.y * DM + (b >> 4) * 128 + t3 * 16 + (b & 15)] = (b & 1) ? r >> 16 : r;
        if (b == 0 && t3 == 0) st_relaxed(&g_epoch, epoch + 1);
      }
      PROF(31, t3 == 0, 36);
    }
    cluster_wait();
  } else {
    const int wg = warp >> 2;

    uint32_t tag;
    {
      uint32_t* const pmod = g_modp + rank * 2 * DM + (b >> 1) * 32 + lane;
      uint32_t* const pln = g_ln1 + (rb * 128 + cj * 16 + warp) * 4;
      uint32_t sc[8];
#pragma unroll
      for (int k = 0; k < 8; k++) sc[k] = ldg_nc1(P.c + rank * 512 + warp * 64 + k * 8 + (lane & 3) * 2);
      const uint32_t epoch = ld_relaxed(&g_epoch);
      if (warp == 0) st_relaxed(pmod, 0);
      if (lane == 0) { st_b128(pln, 0, 0, 0, 0); st_b128(pln + 32, 0, 0, 0, 0); }
      asm volatile("setmaxnreg.inc.sync.aligned.u32 232;");
      bar_sync(1, 320);
#pragma unroll
      for (int k = 0; k < 8; k++) sc[k] = pack_bf(silu_f(bf_lo(sc[k])), silu_f(bf_hi(sc[k])));
      keep(sc);
      tag = epoch % 3 + 1;
#pragma unroll
      for (int part = 0; part < 4; part++) {
        if (!(part & 1)) {
          const uint32_t xa = base + (2 + part / 2) * GST_BYTES + warp * 2048 + lane * 16;
          mbar_wait(bar_hx + part * 4, 0);
          float s0 = 0.f, s1 = 0.f, q0 = 0.f, q1 = 0.f;
#pragma unroll
          for (int q = 0; q < 4; q++) {
            const uint4 xv = lds4(xa + q * 512);
            const uint32_t u[4] = {xv.x, xv.y, xv.z, xv.w};
#pragma unroll
            for (int e = 0; e < 4; e++) { const float lo = bf_lo(u[e]), hi = bf_hi(u[e]); s0 += lo; s1 += hi; q0 += lo * lo; q1 += hi * hi; }
          }
          s0 += s1; q0 += q1;
#pragma unroll
          for (int o = 16; o > 0; o >>= 1) { s0 += __shfl_xor_sync(0xffffffffu, s0, o); q0 += __shfl_xor_sync(0xffffffffu, q0, o); }
          const float mean = s0 * (1.f / DM);
          float mb, sd;
          ln_scalars(mean, fmaxf(q0 * (1.f / DM) - mean * mean, 0.f), mb, sd);
          uint32_t ih, il;
          split_inv(sd, ih, il);
          if (lane == 0) st_b128(pln + part * 16, pack_bf(mb, mb), ih, il, tag);
          PROF(1, tid == 0 && part == 2, 4);
        } else if (late == (part == 3)) {
          const uint32_t fr = (lane & 7) + (lane >> 4) * 8, tq = lane & 3;
          const uint32_t wa = stage + warp * 4096 + fr * 64 + ((((lane >> 3) & 1) ^ ((fr >> 1) & 3)) << 4);
          float d0[4] = {0.f, 0.f, 0.f, 0.f}, d1[4] = {0.f, 0.f, 0.f, 0.f};
          mbar_wait(bar_hw, 0);
#pragma unroll
          for (int ks = 0; ks < 4; ks++) {
            uint32_t w[8];
            ldmatrix4t(wa + ks * 1024, w[0], w[1], w[2], w[3]);
            ldmatrix4t((wa ^ 32) + ks * 1024, w[4], w[5], w[6], w[7]);
            mma16816(d0, w[0], w[1], w[2], w[3], sc[2 * ks], sc[2 * ks + 1]);
            mma16816(d1, w[4], w[5], w[6], w[7], sc[2 * ks], sc[2 * ks + 1]);
          }
          sts1(base + 2 * GST_BYTES + warp * 2048 + (tq * 8 + (lane >> 2)) * 4, __float_as_uint((tq & 2) ? ((tq & 1) ? d1[2] : d1[0]) : ((tq & 1) ? d0[2] : d0[0])));
          bar_sync(1, 256);
          if (warp == 0) {
            float s = 0.f;
#pragma unroll
            for (int w8 = 0; w8 < 8; w8++) s += __uint_as_float(lds1(base + 2 * GST_BYTES + w8 * 2048 + lane * 4));
            st_relaxed(pmod, (__float_as_uint(s) & ~3u) | tag);
          }
          PROF(1, tid == 0, 3);
        }
      }
      cluster_wait();
      if (wg == 1) bar_arrive(2, 256);
    }

    const uint32_t rempty = lane < 2 ? mapa(bempty, lane & 1) : 0;
    constexpr uint32_t GE = NSLOT * 8 + 32;
    float o[64], s[64];
#pragma unroll 1
    for (int ps = 0; ps < 3; ps++) {
      {
        const uint32_t xt = ps == 1 ? XT1 : XT2, wt = ps == 1 ? WT1 : WT2;
        const int nst = ps == 2 ? 28 : 14;
        if (ps == 0) {
          float ga[64], gb[64];
#pragma unroll
          for (int i = 0; i < 64; i++) { ga[i] = 0.f; gb[i] = 0.f; }
          uint32_t a[2][16];
          const uint32_t l = fresh_lane();
          uint32_t fa[4];
#pragma unroll
          for (int kk = 0; kk < 4; kk++) fa[kk] = (base + wg * 8192 + frag_offset(warp)) ^ (kk * 32);
          const uint32_t mt = par + (l & 3) * 16;
          auto fetch = [&](int i, uint32_t (&f)[16], uint32_t z) {
            mbar_wait(xfull + (i & 3) * 8, i >> 2);
#pragma unroll
            for (int kk = 0; kk < 4; kk++) ldmatrix4(fa[kk] + (i & 3) * GST_BYTES + z, f[4 * kk], f[4 * kk + 1], f[4 * kk + 2], f[4 * kk + 3]);
          };
          const bool oddw = warp & 2;
          uint4 r0, r1;
          {
            const uint32_t t7 = (warp & 1) * 64 + (l >> 4) * 32 + (l & 15);
            const uint32_t* pm = g_modp + wg * DM + ((cj * 128 + t7 * 4) & (DM - 1));
            const uint32_t* pr = g_ln1 + (rb * 128 + warp * 16 + (l >> 2)) * 4;
            uint4 m0 = make_uint4(tag, tag, tag, tag), m1 = m0;
            if (!oddw) { m0 = ld_relaxed4(pm); m1 = ld_relaxed4(pm + 2 * DM); }
            r0 = ld_b128(pr); r1 = ld_b128(pr + 32);
            fetch(0, a[0], 0); fetch(1, a[1], 0);
            uint32_t n = 0;
            bool written = false;
#pragma unroll 1
            while (true) {
              uint32_t miss;
              asm volatile("{ .reg .pred p0, p1, p2, p3; .reg .b32 t, u;\n"
                           "lop3.b32 t, %1, %2, %19, 0x7e; lop3.b32 u, %3, %4, %19, 0x7e; or.b32 t, t, u; and.b32 t, t, 3; setp.ne.u32 p0, t, 0;\n"
                           "lop3.b32 t, %5, %6, %19, 0x7e; lop3.b32 u, %7, %8, %19, 0x7e; or.b32 t, t, u; and.b32 t, t, 3; setp.ne.u32 p1, t, 0;\n"
                           "setp.ne.u32 p2, %12, %19; setp.ne.u32 p3, %16, %19;\n"
                           "@p0 ld.relaxed.gpu.global.v4.u32 {%1, %2, %3, %4}, [%17];\n"
                           "@p1 ld.relaxed.gpu.global.v4.u32 {%5, %6, %7, %8}, [%17 + 8192];\n"
                           "@p2 ld.relaxed.gpu.global.v4.u32 {%9, %10, %11, %12}, [%18];\n"
                           "@p3 ld.relaxed.gpu.global.v4.u32 {%13, %14, %15, %16}, [%18 + 128];\n"
                           "or.pred p0, p0, p1; or.pred p2, p2, p3; vote.sync.any.pred p0, p0, 0xffffffff; vote.sync.any.pred p2, p2, 0xffffffff;\n"
                           "selp.u32 t, 1, 0, p0; selp.u32 u, 2, 0, p2; or.b32 %0, t, u; }"
                           : "=r"(miss), "+r"(m0.x), "+r"(m0.y), "+r"(m0.z), "+r"(m0.w), "+r"(m1.x), "+r"(m1.y), "+r"(m1.z), "+r"(m1.w),
                             "+r"(r0.x), "+r"(r0.y), "+r"(r0.z), "+r"(r0.w), "+r"(r1.x), "+r"(r1.y), "+r"(r1.z), "+r"(r1.w)
                           : "l"(pm), "l"(pr), "r"(tag) : "memory");
              if (!(miss & 1) && !written) {
                written = true;
                if (!oddw) write_table(par, wg, t7, m0, m1);
                mbar_arrive(bar_mod);
              }
              if (!miss) break;
              watchdog(n);
            }
          }
          const uint32_t zero = r0.w ^ tag;
          auto normalize = [&](uint32_t (&f)[16]) {
#pragma unroll
            for (int k = 0; k < 16; k += 2) { f[k] = ln_norm(f[k], r0.x, r0.y, r0.z); f[k + 1] = ln_norm(f[k + 1], r1.x, r1.y, r1.z); }
          };
          auto modulate = [&](int i, uint32_t (&f)[16]) {
#pragma unroll
            for (int kk = 0; kk < 4; kk++) {
              const uint4 m = lds4(mt + slice_of(i) * 256 + kk * 64);
              f[4 * kk] = hfma2(f[4 * kk], m.x, m.z); f[4 * kk + 1] = hfma2(f[4 * kk + 1], m.x, m.z);
              f[4 * kk + 2] = hfma2(f[4 * kk + 2], m.y, m.w); f[4 * kk + 3] = hfma2(f[4 * kk + 3], m.y, m.w);
            }
            keep(f);
            mbar_arrive_pred(xempty + (i & 3) * 8, l == 0);
          };
          auto publish = [&](int u, uint32_t (&f)[16]) {
#pragma unroll
            for (int kk = 0; kk < 4; kk++) stmatrix4(fa[kk] + OFF_STAGE + u * UNIT, f[4 * kk], f[4 * kk + 1], f[4 * kk + 2], f[4 * kk + 3]);
            __syncwarp();
            mbar_arrive_pred(bar_hpub + u * 8, l == 0);
          };
          auto multiply = [&](int i, uint32_t (&f)[16]) {
            mbar_wait(gfull + (i & 3) * 8, i >> 2);
            const uint64_t db = make_desc(base + (i & 3) * GST_BYTES + UNIT, 8192, 1024);
            wg_fence();
#pragma unroll
            for (int kk = 0; kk < 4; kk++) mma256_rs(ga, gb, f[4 * kk], f[4 * kk + 1], f[4 * kk + 2], f[4 * kk + 3], db + kk * 128);
            wg_commit();
          };
          auto next = [&](int i, uint32_t (&f)[16]) {
            wg_wait<1>();
            mbar_arrive_cl(rempty, GE + ((i + 2) & 3) * 8);
            uint32_t z = zero;
#pragma unroll
            for (int k = 0; k < 16; k += 2) asm volatile("lop3.b32 %0, %1, %2, %0, 0xA8;" : "+r"(z) : "r"(f[k]), "r"(f[k + 1]));
            fetch(i, f, z);
            normalize(f);
            if (i == 2) { keep(f); mbar_wait(bar_mod2, 0); }
            modulate(i, f); multiply(i, f);
          };
          normalize(a[0]); normalize(a[1]);
          keep(a[0]); keep(a[1]);
          mbar_wait(bar_mod, 0);
          PROF(1, tid == 0, 2);
          modulate(0, a[0]); multiply(0, a[0]); publish(0, a[0]);
          modulate(1, a[1]); multiply(1, a[1]);
#pragma unroll 1
          for (int i = 2; i < NRS; i += 2) {
            next(i, a[0]);
            if (i == 2) publish(1, a[0]);
            next(i + 1, a[1]);
          }
          wg_wait<1>();
          mbar_arrive_cl(rempty, GE + ((NRS + 2) & 3) * 8);
#pragma unroll 1
          for (int i = NRS; i < 14; i++) {
            mbar_wait(xfull + (i & 3) * 8, (i >> 2) & 1);
            mbar_wait(gfull + (i & 3) * 8, (i >> 2) & 1);
            const uint32_t xa = base + (i & 3) * GST_BYTES;
            const uint64_t da = make_desc(xa + wg * 8192, 16, 1024), db = make_desc(xa + UNIT, 8192, 1024);
            if (i == 13) bar_sync(2 + wg, 256);
            wg_fence();
#pragma unroll
            for (int kk = 0; kk < 4; kk++) mma256_ss(ga, gb, da + kk * 2, db + kk * 128, 1);
            wg_commit();
            if (i == 13) bar_arrive(3 - wg, 256);
            wg_wait<1>();
            uint32_t z = zero;
#pragma unroll
            for (int k = 0; k < 16; k += 2) asm volatile("lop3.b32 %0, %1, %2, %0, 0xA8;" : "+r"(z) : "r"(a[1][k]), "r"(a[1][k + 1]));
            mbar_arrive_cl(rempty, GE + ((i + 3) & 3) * 8 + z);
            mbar_arrive_pred(xempty + ((i + 3) & 3) * 8, l == 0 && i != NRS);
          }
          mbar_wait(xfull + 16, 1);
          wg_wait<0>();
          keep(ga); keep(gb);
#pragma unroll
          for (int i = 0; i < 64; i++) {
            asm volatile("mov.b32 %0, %1;" : "=f"(s[i]) : "f"(ga[i]));
            asm volatile("mov.b32 %0, %1;" : "=f"(o[i]) : "f"(gb[i]));
          }
        } else {
          float ga[64], gb[64];
#pragma unroll
          for (int i = 0; i < 64; i++) {
            asm volatile("mov.b32 %0, %1;" : "=f"(ga[i]) : "f"(s[i]));
            asm volatile("mov.b32 %0, %1;" : "=f"(gb[i]) : "f"(o[i]));
          }
#pragma unroll 1
          for (int i = 0; i < nst; i++) {
            mbar_wait(gfull + (i & 3) * 8, (i >> 2) & 1);
            const uint64_t da = make_desc(base + unit_of(xt, i & 3) + wg * 8192, 16, 1024), db = make_desc(base + unit_of(wt, i & 3), 8192, 1024);
            if (i == nst - 1) bar_sync(2 + wg, 256);
            wg_fence();
#pragma unroll
            for (int kk = 0; kk < 4; kk++) mma256_ss(ga, gb, da + kk * 2, db + kk * 128, kk ? 1 : i);
            wg_commit();
            if (i == nst - 1) bar_arrive(3 - wg, 256);
            wg_wait<1>();
            mbar_arrive_cl(rempty, GE + ((i + 3) & 3) * 8, i != 0);
            PROF(4, tid == 0 && (i & 3) == 0, 40 + (ps - 1) * 4 + i / 4);
          }
          wg_wait<0>();
          keep(ga); keep(gb);
#pragma unroll
          for (int i = 0; i < 64; i++) {
            asm volatile("mov.b32 %0, %1;" : "=f"(s[i]) : "f"(ga[i]));
            asm volatile("mov.b32 %0, %1;" : "=f"(o[i]) : "f"(gb[i]));
          }
        }
        mbar_arrive_cl(rempty, GE + (ps == 2 ? 24 : 8));
        if (ps == 2) break;
      }
      const uint32_t qw = base + wg * 8192, qt = QT >> (16 * ps), at = ps ? AT1 : AT0;
      {
        const uint32_t wt = ps ? WT1 : WT0;
        const uint64_t da0 = make_desc(qw + unit_of(qt, 2), 16, 1024), da1 = make_desc(qw + unit_of(qt, 3), 16, 1024);
        const uint64_t db0 = make_desc(base + unit_of(wt, 2), 8192, 1024), db1 = make_desc(base + unit_of(wt, 3), 8192, 1024);
        mbar_wait(gfull + 16, 1);
        bar_sync(2 + wg, 256);
        wg_fence();
#pragma unroll
        for (int kk = 0; kk < 4; kk++) mma_ss<1>(s, da0 + kk * 2, db0 + kk * 128, 1);
        wg_commit();
        mbar_wait(xfull + 24, 1);
        mbar_wait(gfull + 24, 1);
        wg_fence();
#pragma unroll
        for (int kk = 0; kk < 4; kk++) mma_ss<1>(s, da1 + kk * 2, db1 + kk * 128, 1);
        wg_commit();
        bar_arrive(3 - wg, 256);
        mbar_wait(ps == 0 ? bar_pread : bar_ofree + 8, 0);
        wg_wait<0>();
        keep(s);
        PROF(2, tid == 0, 8 + ps * 8);
        uint32_t q[32];
        pack_p(s, q);
#pragma unroll
        for (int i = 0; i < 4; i++) stmatrix4((qw + unit_of(qt, 0) + frag_offset(warp)) ^ (i << 5), q[4 * i], q[4 * i + 1], q[4 * i + 2], q[4 * i + 3]);
        keep(q);
        bar_sync(2 + wg, 256);
        wg_fence();
#pragma unroll
        for (int kk = 0; kk < 8; kk++) mma_ss<1>(o, (kk < 4 ? da0 : da1) + (kk & 3) * 2, (kk < 4 ? db0 : db1) + UNIT / 16 + (kk & 3) * 128, 1);
        wg_commit();
        mbar_wait(bfull, 0);
        wg_fence();
        const uint64_t dk = make_desc(base + unit_of(at, 0), 16, 1024);
#pragma unroll
        for (int kk = 0; kk < 8; kk++) mma_rs<0>(s, q[4 * kk], q[4 * kk + 1], q[4 * kk + 2], q[4 * kk + 3], dk + (kk >> 2) * 1024 + (kk & 3) * 2, kk != 0);
        wg_commit();
        bar_arrive(3 - wg, 256);
#pragma unroll
        for (int i = 4; i < 8; i++) stmatrix4((qw + unit_of(qt, 1) + frag_offset(warp)) ^ ((i & 3) << 5), q[4 * i], q[4 * i + 1], q[4 * i + 2], q[4 * i + 3]);
        wg_wait<1>();
        keep(o);
        mbar_arrive_cl(rempty, GE + 16);
        mbar_arrive_cl(rempty, GE + 24);
        store_chunk<0>(o, qw + unit_of(qt, 2) + frag_offset(warp));
        store_chunk<1>(o, qw + unit_of(qt, 3) + frag_offset(warp));
        wg_wait<0>();
        keep(s);
        mbar_arrive_cl(rempty, 0);
      }
      PROF(4, tid == 0 && ps == 1, 61);
      float l0 = 0.f, l1 = 0.f, f0 = 0.f, f1 = 0.f;
      auto step = [&](auto odd_c, const int j, uint32_t (&pw)[32], uint32_t (&pr)[32]) {
        constexpr bool ODD = decltype(odd_c)::value;
        const bool first = !ODD && (j & 2) == 0, last = ODD && j == 7;
        const uint32_t ph = (j >> 1) & 1;
        float i0, i1, a0, a1;
        const bool so = !ODD && j == 4;
        if (so) { i0 = inv_quad_sum(l0); i1 = inv_quad_sum(l1); l0 = 0.f; l1 = 0.f; }
        if (first) {
          int m0 = max(__float_as_int(s[0]), __float_as_int(s[1])), m1 = max(__float_as_int(s[2]), __float_as_int(s[3]));
#pragma unroll
          for (int i = 1; i < 16; i++) {
            m0 = __vimax3_s32(m0, __float_as_int(s[4 * i]), __float_as_int(s[4 * i + 1]));
            m1 = __vimax3_s32(m1, __float_as_int(s[4 * i + 2]), __float_as_int(s[4 * i + 3]));
          }
          m0 = max(m0, __shfl_xor_sync(0xffffffffu, m0, 1)); m1 = max(m1, __shfl_xor_sync(0xffffffffu, m1, 1));
          m0 = max(m0, __shfl_xor_sync(0xffffffffu, m0, 2)); m1 = max(m1, __shfl_xor_sync(0xffffffffu, m1, 2));
          f0 = fmaf(__int_as_float(m0), SCL2, BIAS); f1 = fmaf(__int_as_float(m1), SCL2, BIAS);
        }
        bool redo = false;
        while (true) {
          if (redo) {
            float m0 = fmaxf(s[0], s[1]), m1 = fmaxf(s[2], s[3]);
#pragma unroll
            for (int i = 1; i < 16; i++) { m0 = fmaxf(m0, fmaxf(s[4 * i], s[4 * i + 1])); m1 = fmaxf(m1, fmaxf(s[4 * i + 2], s[4 * i + 3])); }
            m0 = fmaxf(m0, __shfl_xor_sync(0xffffffffu, m0, 1)); m1 = fmaxf(m1, __shfl_xor_sync(0xffffffffu, m1, 1));
            m0 = fmaxf(m0, __shfl_xor_sync(0xffffffffu, m0, 2)); m1 = fmaxf(m1, __shfl_xor_sync(0xffffffffu, m1, 2));
            m0 = fmaf(m0, SCL2, BIAS); m1 = fmaf(m1, SCL2, BIAS);
            if (!first) {
              m0 = fmaxf(m0, f0); m1 = fmaxf(m1, f1);
              const float c0 = ex2(f0 - m0), c1 = ex2(f1 - m1);
              l0 *= c0; l1 *= c1;
              wg_wait<0>();
              keep(o);
#pragma unroll
              for (int i = 0; i < 16; i++) { o[4 * i] *= c0; o[4 * i + 1] *= c0; o[4 * i + 2] *= c1; o[4 * i + 3] *= c1; }
            }
            f0 = m0; f1 = m1;
          }
          float b0 = 0.f, b1 = 0.f;
          a0 = 0.f; a1 = 0.f;
#pragma unroll
          for (int i = 0; i < 16; i++) {
            const float e0 = ex2(fmaf(s[4 * i], SCL2, -f0)), e1 = ex2(fmaf(s[4 * i + 1], SCL2, -f0));
            const float e2 = ex2(fmaf(s[4 * i + 2], SCL2, -f1)), e3 = ex2(fmaf(s[4 * i + 3], SCL2, -f1));
            a0 += e0; b0 += e1; a1 += e2; b1 += e3;
            pw[2 * i] = pack_bf(e0, e1); pw[2 * i + 1] = pack_bf(e2, e3);
            if (i == VREL) {
#pragma unroll
              for (int k = 0; k < 2 * VREL + 2; k++) asm volatile("" : "+r"(pw[k])::"memory");
              mbar_wait(bar_mod, 0);
              wg_wait<0>();
              mbar_arrive_cl(rempty, ODD ? 16 : 0, !redo && (ODD || j));
#pragma unroll
              for (int k = 4 * VREL + 4; k < 64; k++) asm volatile("" : "+f"(s[k])::"memory");
            }
          }
          a0 += b0; a1 += b1;
          if (redo) break;
          redo = __any_sync(0xffffffffu, !(a0 + a1 < 1.f));
          if (!redo) break;
        }
        l0 += a0; l1 += a1;
        keep(pw);
        keep(o);
        if (so) store_chunk<0>(o, i0, i1, qw + unit_of(qt, 0) + frag_offset(warp));
        keep(o);
        if (j == (ODD ? 5 : 0)) { fence_async_smem(); if (ODD) mbar_arrive(bar_ofull + wg * 8); }
        mbar_wait(bfull + (ODD ? 24 : 8), ph);
        bar_sync(2 + wg, 256);
        if (!last) {
          const uint32_t qn = qt >> (j >= 3 ? 8 : 0);
          wg_fence();
          issue_qk(s, qw + unit_of(qn, 0), qw + unit_of(qn, 1), base + unit_of(at, ODD ? 3 : 1));
          wg_commit();
          mbar_wait(bfull + (ODD ? 0 : 16), ODD ? ph ^ 1 : ph);
        }
        if (so) { store_chunk<1>(o, i0, i1, qw + unit_of(qt, 1) + frag_offset(warp)); keep(o); }
        wg_fence();
        issue_pv(o, pw, base + unit_of(at, ODD ? (last ? 3 : 0) : 2), !first);
        wg_commit();
        bar_arrive(3 - wg, 256);
        wg_wait<1>();
        keep(s);
        mbar_arrive_cl(rempty, ODD ? 24 : 8, !last);
        PROF(4, tid == 0 && ps == 1, 51 + j);
      };
      uint32_t pa[32], pb[32];
#pragma unroll 1
      for (int j = 0; j < 8; j += 2) {
        step(std::false_type{}, j, pa, pb);
        step(std::true_type{}, j + 1, pb, pa);
      }
      {
        const float i0 = inv_quad_sum(l0), i1 = inv_quad_sum(l1);
        wg_wait<0>();
        keep(o);
        mbar_arrive_cl(rempty, 24);
        store_chunk<0>(o, i0, i1, qw + unit_of(qt, 2) + frag_offset(warp));
        store_chunk<1>(o, i0, i1, qw + unit_of(qt, 3) + frag_offset(warp));
        fence_async_smem();
        mbar_arrive(bar_ofull + 16 + wg * 8);
      }
      PROF(2, tid == 0, 10 + ps * 8);
    }

    const int ln = fresh_lane(), g = ln >> 2, tq = ln & 3, ct = warp * 32 + ln;
    const bool lane0 = ln == 0;
    const int lrow0 = warp * 16 + g;
    const uint32_t res = base + OFF_RES, trow = res + wg * 8192 + frag_offset(warp);
    uint32_t xr[32];
    uint4 sv[4], own;
    uint32_t* const sg = g_stats + (rb * 8 + warp) * 512 + g * 4;
    uint32_t* sp[4];
#pragma unroll
    for (int k = 0; k < 4; k++) sp[k] = sg + (tq & 1) * 32 + (((tq >> 1) ^ (cj >> 2)) * 4 + (k ^ (cj & 3))) * 64;
    {
      const uint64_t da = make_desc(base + wg * 8192, 16, 1024), db = make_desc(base, 8192, 1024);
      constexpr int U = UNIT / 16;
#define HALF_STAGE(acc, xu, wu) _Pragma("unroll") for (int kk = 0; kk < 4; kk++) mma_ss<1>(acc, da + (xu) * U + kk * 2, db + (wu) * U + kk * 128, 1)
      PROF(10, ct == PT, 19); STAMP(0);
      cluster_arrive();
      mbar_wait(gfull, 1);
      mbar_wait(gfull + 8, 1);
      bar_sync(2 + wg, 256);
      wg_fence();
      HALF_STAGE(o, 7, 1);
      HALF_STAGE(o, 8, 3);
      wg_commit();
      STAMP(16);
      mbar_wait(gfull + 16, 1);
      STAMP(17);
      wg_fence();
      HALF_STAGE(o, 6, 11);
      wg_commit();
      bar_arrive(3 - wg, 256);
      mbar_wait(bar_par, 0);
      uint32_t* xo = g_xch + ((size_t)b * 8 * 256 + ct) * 4;
      const uint32_t* xi = g_xch + ((size_t)(b ^ 2) * 8 * 256 + ct) * 4;
      const uint32_t par1 = (~lds1(par + PAR_CONST + 4) & 1) << 16;
      wg_wait<1>();
      mbar_arrive_pred(bar_rel, lane0);
      wg_wait<0>();
      keep(o);
      mbar_arrive_pred(bar_ring, lane0);
      PROF(8, ct == PT, 20); STAMP(1);
#define SEND(i) st_b128(xo + (i) * 1024, (pack_bf(o[8 * (i)], o[8 * (i) + 1]) & ~0x10000u) | par1, pack_bf(o[8 * (i) + 2], o[8 * (i) + 3]), \
                        pack_bf(o[8 * (i) + 4], o[8 * (i) + 5]), pack_bf(o[8 * (i) + 6], o[8 * (i) + 7]))
#pragma unroll
      for (int i = 0; i < NS1; i++) SEND(i);
      PROF(8, ct == PT, 21); STAMP(2);
      bar_sync(2 + wg, 256);
      wg_fence();
      HALF_STAGE(s, 7, 0);
      HALF_STAGE(s, 8, 2);
      HALF_STAGE(s, 6, 10);
      wg_commit();
      bar_arrive(3 - wg, 256);
      STAMP(18);
      mbar_wait(gfull + 24, 1);
#pragma unroll
      for (int i = NS1; i < 8; i++) SEND(i);
      uint4 v[8];
      STAMP(19);
      mbar_wait(bar_xres, 0);
      wg_wait<0>();
      mbar_arrive_pred(bar_ring + 8, lane0);
      bar_sync(2 + wg, 256);
      STAMP(20);
#pragma unroll
      for (int i = 0; i < LD2; i++) v[i] = ld_b128(xi + i * 1024);
      mbar_wait(bar_xres, 0);
      wg_fence();
      HALF_STAGE(s, 9, 4);
      wg_commit();
      mbar_wait(bar_rx, 0);
      wg_fence();
      HALF_STAGE(s, 1, 5);
      wg_commit();
      bar_arrive(3 - wg, 256);
      STAMP(21);
#pragma unroll
      for (int i = LD2; i < 8; i++) v[i] = ld_b128(xi + i * 1024);
      mbar_wait(bar_xres, 0);
      wg_wait<0>();
      keep(s);
      mbar_arrive_pred(bar_ring + 16, lane0);
      PROF(10, ct == PT, 23); STAMP(4);
#pragma unroll
      for (int i = 0; i < 16; i += 2) ldmatrix4((trow ^ ((i & 7) << 4)) + (i >> 3) * 16384, xr[2 * i], xr[2 * i + 1], xr[2 * i + 2], xr[2 * i + 3]);
      uint32_t ga[16];
      uint4 bw[8];
#pragma unroll
      for (int i = 0; i < 8; i++) {
        if (!(i & 1)) {
          const uint4 t = lds4(par + PAR_SINK + i * 32 + tq * 16);
          ga[2 * i] = t.x; ga[2 * i + 1] = t.y; ga[2 * i + 2] = t.z; ga[2 * i + 3] = t.w;
        }
        bw[i] = lds4(par + PAR_T1 + i * 64 + tq * 16);
        if (!(g & 1)) { bw[i].x = 0x3f803f80u; bw[i].y = 0x3f803f80u; }
      }
      uint32_t pk[32];
      pack_p(s, pk);
      const uint32_t par2 = (~lds1(par + PAR_CONST + 12) & 1) << 16;
      {
        uint32_t n = 0, miss;
        do {
          miss = 0;
#pragma unroll
          for (int i = 0; i < 8; i++) miss |= v[i].x ^ par2;
          miss = __any_sync(0xffffffffu, miss & 0x10000u);
          if (miss) {
#pragma unroll
            for (int i = 0; i < 8; i++)
              asm volatile("{ .reg .pred p; .reg .b32 t; xor.b32 t, %0, %5; and.b32 t, t, 0x10000; setp.ne.u32 p, t, 0;\n"
                           "@p ld.relaxed.gpu.global.v4.u32 {%0, %1, %2, %3}, [%4]; }"
                           : "+r"(v[i].x), "+r"(v[i].y), "+r"(v[i].z), "+r"(v[i].w) : "l"(xi + i * 1024), "r"(par1) : "memory");
          }
          watchdog(n);
        } while (miss);
      }
      PROF(8, ct == PT, 22); STAMP(3);
      float ds[4] = {0.f, 0.f, 0.f, 0.f}, dl[4] = {0.f, 0.f, 0.f, 0.f}, q0[4] = {0.f, 0.f, 0.f, 0.f}, q1[4] = {0.f, 0.f, 0.f, 0.f};
#pragma unroll
      for (int i = 0; i < 8; i++) {
        const uint32_t u0 = hfma2(ga[2 * i], hadd2(pk[4 * i], v[i].x & ~0x10000u), xr[4 * i]);
        const uint32_t u1 = hfma2(ga[2 * i], hadd2(pk[4 * i + 1], v[i].y), xr[4 * i + 1]);
        const uint32_t u2 = hfma2(ga[2 * i + 1], hadd2(pk[4 * i + 2], v[i].z), xr[4 * i + 2]);
        const uint32_t u3 = hfma2(ga[2 * i + 1], hadd2(pk[4 * i + 3], v[i].w), xr[4 * i + 3]);
        xr[4 * i] = u0; xr[4 * i + 1] = u1; xr[4 * i + 2] = u2; xr[4 * i + 3] = u3;
        mma16816(ds, u0, u1, u2, u3, bw[i].x, bw[i].y);
        mma16816(dl, u0, u1, u2, u3, bw[i].z, bw[i].w);
        mma16816(q0, u0, u1, u2, u3, u0, u2);
        mma16816(q1, u0, u1, u2, u3, u1, u3);
      }
      const float sqa = (g & 1) ? q0[1] : q0[0], sqb = (g & 1) ? q1[3] : q1[2], dta = ds[1] + dl[1], dtb = ds[3] + dl[3];
      if (tq == (g >> 1)) {
        st_b128(sg + cj * 64, __float_as_uint(ds[0]), __float_as_uint(sqa), __float_as_uint(dta), tag);
        st_b128(sg + cj * 64 + 32, __float_as_uint(ds[2]), __float_as_uint(sqb), __float_as_uint(dtb), tag);
      }
#pragma unroll
      for (int k = 0; k < 4; k++) sv[k] = ld_b128(sp[k]);
      mbar_wait(bar_xres, 0);
      const float sqc = __shfl_sync(0xffffffffu, sqa, g * 4 + (g >> 1)), sqd = __shfl_sync(0xffffffffu, sqb, g * 4 + (g >> 1));
      own = (tq & 1) ? make_uint4(__float_as_uint(ds[2]), __float_as_uint(sqd), __float_as_uint(dtb), tag)
                     : make_uint4(__float_as_uint(ds[0]), __float_as_uint(sqc), __float_as_uint(dta), tag);
    }
    PROF(8, ct == PT, 29); STAMP(5);
    uint32_t mm, ih, il;
    float rbest;
    uint32_t wf[128];
    const uint32_t frow = (ln & 7) + (ln >> 4) * 8;
    const uint32_t wfo = base + (warp & 1) * 8192 + frow * 64 + ((((ln >> 3) & 1) ^ ((frow >> 1) & 3)) << 4);
#define LOAD_WF(m) _Pragma("unroll") for (int f = 0; f < 16; f++) {                                                   \
      const int r = ((f >> 1) * 4 + (m) * 2 + (f & 1)) * 4;                                                           \
      ldmatrix4t(((wfo + unit_of((m) ? FT_U : FT_G, warp >> 1)) ^ ((f & 1) * 32)) + (f >> 1) * 1024, wf[r], wf[r + 1], wf[r + 2], wf[r + 3]); \
    }
    bool early;
    {
#pragma unroll
      for (int i = 0; i < 16; i += 2) stmatrix4((trow ^ ((i & 7) << 4)) + (i >> 3) * 16384, xr[2 * i], xr[2 * i + 1], xr[2 * i + 2], xr[2 * i + 3]);
      const uint4 cst = lds4(par + PAR_CONST);
      const float A1 = __uint_as_float(cst.x), A2 = __uint_as_float(cst.z);
      uint32_t n = 0;
      early = false;
#pragma unroll 1
      while (true) {
        if (!early && (b >= NFFN || __all_sync(0xffffffffu, mbar_test(bar_box + (warp >> 1) * 8, 0)))) {
          early = true;
          LOAD_WF(0);
          __syncwarp();
          mbar_arrive_pred(bar_gate, lane0);
        }
        uint32_t miss;
        asm volatile("{ .reg .pred p0, p1, p2, p3; .reg .b64 u, v; .reg .b128 w;\n"
                     "setp.ge.u32 p0, %22, 2; setp.ne.and.u32 p0, %4, %21, p0; setp.ne.u32 p1, %8, %21; setp.ne.u32 p2, %12, %21; setp.ne.u32 p3, %16, %21;\n"
                     "@p0 ld.relaxed.gpu.global.v4.u32 {%1, %2, %3, %4}, [%17];\n"
                     "@p1 ld.relaxed.gpu.global.v4.u32 {%5, %6, %7, %8}, [%18];\n"
                     "@p2 ld.relaxed.gpu.global.v4.u32 {%9, %10, %11, %12}, [%19];\n"
                     "@p3 ld.relaxed.gpu.global.v4.u32 {%13, %14, %15, %16}, [%20];\n"
                     "or.pred p0, p0, p1; or.pred p2, p2, p3; or.pred p0, p0, p2; vote.sync.any.pred p0, p0, 0xffffffff; selp.u32 %0, 1, 0, p0; }"
                     : "=r"(miss), "+r"(sv[0].x), "+r"(sv[0].y), "+r"(sv[0].z), "+r"(sv[0].w), "+r"(sv[1].x), "+r"(sv[1].y), "+r"(sv[1].z), "+r"(sv[1].w),
                       "+r"(sv[2].x), "+r"(sv[2].y), "+r"(sv[2].z), "+r"(sv[2].w), "+r"(sv[3].x), "+r"(sv[3].y), "+r"(sv[3].z), "+r"(sv[3].w)
                     : "l"(sp[0]), "l"(sp[1]), "l"(sp[2]), "l"(sp[3]), "r"(tag), "r"(tq) : "memory");
        if (!miss) break;
        watchdog(n);
      }
      const uint4 v0 = tq < 2 ? own : sv[0], v1 = sv[1], v2 = sv[2], v3 = sv[3];
      PROF(8, ct == PT, 30); STAMP(6);
      float su = (__uint_as_float(v0.x) + __uint_as_float(v1.x)) + (__uint_as_float(v2.x) + __uint_as_float(v3.x));
      float sq = (__uint_as_float(v0.y) + __uint_as_float(v1.y)) + (__uint_as_float(v2.y) + __uint_as_float(v3.y));
      float dt = (__uint_as_float(v0.z) + __uint_as_float(v1.z)) + (__uint_as_float(v2.z) + __uint_as_float(v3.z));
      su += __shfl_xor_sync(0xffffffffu, su, 2); sq += __shfl_xor_sync(0xffffffffu, sq, 2); dt += __shfl_xor_sync(0xffffffffu, dt, 2);
      const float m = su * (1.f / DM);
      float mb, sd;
      ln_scalars(m, fmaxf(sq * (1.f / DM) - m * m, 0.f), mb, sd);
      const float inv = rcp(sd);
      rbest = (dt - mb * A1) * inv + A2;
      mm = pack_bf(mb, mb);
      ih = pack_bf(inv, inv);
      const float lo = inv - bf_lo(ih);
      il = pack_bf(lo, lo);
    }
    int ibest;
    {
      const uint32_t bits = __float_as_uint(rbest);
      const uint32_t key = (((int)bits < 0 ? ~bits : bits | 0x80000000u) & ~0x1ffu) | ((127 - lrow0 - (tq & 1) * 8) << 2) | tag;
      sts1(par + PAR_RED + warp * 4, __reduce_max_sync(0xffffffffu, key));
      PROF(8, ct == PT, 38); STAMP(7);
      bar_sync(1, 256);
      const uint4 ka = lds4(par + PAR_RED), kb = lds4(par + PAR_RED + 16);
      const uint32_t k2 = max(max(max(ka.x, ka.y), max(ka.z, ka.w)), max(max(kb.x, kb.y), max(kb.z, kb.w)));
      if (ct < CR && cj == 0) st_relaxed(g_cand + ct * 512 + rb * CS, k2);
      ibest = 127 - ((k2 >> 2) & 127);
    }
    PROF(8, ct == PT, 39); STAMP(8);
    if ((ibest >> 4) == warp) {
      const int src = (ibest & 7) * 4 + ((ibest >> 3) & 1), ch = g * 2;
      const uint32_t cm = __shfl_sync(0xffffffffu, mm, src), ch_ = __shfl_sync(0xffffffffu, ih, src), cl = __shfl_sync(0xffffffffu, il, src);
      const uint32_t xa = res + (ch >> 3) * 16384 + ibest * 128 + (((ch & 7) ^ (ibest & 7)) << 4) + tq * 4;
      const uint32_t x0 = lds1(xa), x1 = lds1(xa ^ 16);
      const uint2 p0 = lds2(par + PAR_T2 + ch * 64 + tq * 16), p1 = lds2(par + PAR_T2 + ch * 64 + 64 + tq * 16);
      uint32_t* dst = g_row + rb * 2 * DM + cj * 128 + ln * 4;
      st_pairs(dst, ln_mod(x0, cm, ch_, cl, p0.x, p0.y), ln_mod(x1, cm, ch_, cl, p1.x, p1.y), tag);
      st_pairs(dst + DM, x0, x1, tag);
      __syncwarp();
    }
    PROF(8, ct == PT, 37); STAMP(9);
    uint32_t wd[64];
    const uint32_t wda = base + unit_of(FT_D, warp >> 1) + (warp & 1) * 8192 + frow * 128 + ((((ln >> 3) & 1) ^ (ln & 7)) << 4);
#define LOAD_WD(f) ldmatrix4t((wda ^ ((((f) >> 1) & 3) * 32)) + ((f) >> 3) * 4096 + ((f) & 1) * 2048, wd[4 * (f)], wd[4 * (f) + 1], wd[4 * (f) + 2], wd[4 * (f) + 3])
    if (!early) {
      if (b < NFFN) mbar_wait(bar_box + (warp >> 1) * 8, 0);
      LOAD_WF(0);
      __syncwarp();
      mbar_arrive_pred(bar_gate, lane0);
    }
    if (b < NFFN) {
      const uint32_t own = base + unit_of(FT_G, warp >> 1) + (warp & 1) * 8192;
      mbar_wait(bar_box + (4 + (warp >> 1)) * 8, 0);
      LOAD_WF(1);
      uint32_t* const ydst = ypart_slot(b, warp * 16 + (tq & 1) * 8 + g);
      PROF(8, ct == PT, 31); STAMP(10);
      bool wdok;
      {
        uint32_t n = 0;
        while (!(wdok = __all_sync(0xffffffffu, mbar_test(bar_box + (8 + (warp >> 1)) * 8, 0))) && !__all_sync(0xffffffffu, mbar_test(bar_sel, 0))) watchdog(n);
      }
      if (wdok) {
#pragma unroll
        for (int f = 0; f < 16; f++) LOAD_WD(f);
      }
      STAMP(11);
      mbar_wait(bar_sel, 0);
      PROF(8, ct == PT, 33); STAMP(12);
      float d[8][4];
#pragma unroll
      for (int i = 0; i < 4; i++) { d[i][0] = 0.f; d[i][1] = 0.f; d[i][2] = 0.f; d[i][3] = 0.f; }
#pragma unroll
      for (int ks = 0; ks < 8; ks++) {
        const uint2 hb = lds2(own + 256 + ks * 32 + tq * 8);
#pragma unroll
        for (int mt = 0; mt < 4; mt++) {
          const int r = ks * 16 + mt * 4;
          mma16816(d[mt], wf[r], wf[r + 1], wf[r + 2], wf[r + 3], hb.x, hb.y);
        }
      }
      sts2(own + (tq * 8 + g) * 8, __float_as_uint((tq & 2) ? ((tq & 1) ? d[1][2] : d[1][0]) : ((tq & 1) ? d[0][2] : d[0][0])),
           __float_as_uint((tq & 2) ? ((tq & 1) ? d[3][2] : d[3][0]) : ((tq & 1) ? d[2][2] : d[2][0])));
      bar_sync(1, 256);
      uint32_t ab[4];
      {
        float G = 0.f, U = 0.f;
        uint2 pv[8];
#pragma unroll
        for (int w8 = 0; w8 < 8; w8++) pv[w8] = lds2(base + ln * 8 + ((FT_G >> (w8 >> 1) * 4) & 15) * UNIT + (w8 & 1) * 8192);
#pragma unroll
        for (int w8 = 0; w8 < 8; w8 += 2) {
          G += __uint_as_float(pv[w8].x) + __uint_as_float(pv[w8 + 1].x);
          U += __uint_as_float(pv[w8].y) + __uint_as_float(pv[w8 + 1].y);
        }
        const float act = rbf(silu_f(rbf(G))) * rbf(U);
        const uint32_t pk = pack_bf(act, __shfl_down_sync(0xffffffffu, act, 1));
#pragma unroll
        for (int i = 0; i < 4; i++) ab[i] = __shfl_sync(0xffffffffu, pk, i * 8 + tq * 2);
      }
      if (!wdok) {
        mbar_wait(bar_box + (8 + (warp >> 1)) * 8, 0);
#pragma unroll
        for (int f = 0; f < 16; f++) LOAD_WD(f);
      }
      PROF(8, ct == PT, 34); STAMP(13);
#pragma unroll
      for (int mt = 0; mt < 8; mt++) {
        d[mt][0] = 0.f; d[mt][1] = 0.f; d[mt][2] = 0.f; d[mt][3] = 0.f;
        mma16816(d[mt], wd[mt * 8], wd[mt * 8 + 1], wd[mt * 8 + 2], wd[mt * 8 + 3], ab[0], ab[1]);
        mma16816(d[mt], wd[mt * 8 + 4], wd[mt * 8 + 5], wd[mt * 8 + 6], wd[mt * 8 + 7], ab[2], ab[3]);
      }
      uint32_t yw[4];
#pragma unroll
      for (int i = 0; i < 4; i++) yw[i] = (tq & 1) ? pack_bf(d[2 * i][2], d[2 * i + 1][2]) : pack_bf(d[2 * i][0], d[2 * i + 1][0]);
      if (tq < 2) st_b128(ydst, (yw[0] & ~1u) | (tag & 1), (yw[1] & ~1u) | (tag >> 1), yw[2], yw[3]);
      PROF(8, ct == PT, 35); STAMP(14);
    }
    mbar_wait(bar_sel, 0);
    mbar_arrive_pred(bar_win, ct == 0);
    const int iwin = lds1(par + PAR_CONST + 60) & 0x7ff;
    const bool cand = (iwin >> 4) == rb * 8 + warp;
    {
      const uint32_t mm0 = __shfl_sync(0xffffffffu, mm, ln & ~1), mm1 = __shfl_sync(0xffffffffu, mm, ln | 1);
      const uint32_t ih0 = __shfl_sync(0xffffffffu, ih, ln & ~1), ih1 = __shfl_sync(0xffffffffu, ih, ln | 1);
      const uint32_t il0 = __shfl_sync(0xffffffffu, il, ln & ~1), il1 = __shfl_sync(0xffffffffu, il, ln | 1);
#pragma unroll 1
      for (int hf = 0; hf < 2; hf++) {
        uint32_t x[16];
#pragma unroll
        for (int i = 0; i < 8; i += 2) ldmatrix4((trow ^ (i << 4)) + hf * 16384, x[2 * i], x[2 * i + 1], x[2 * i + 2], x[2 * i + 3]);
#pragma unroll
        for (int i = 0; i < 8; i++) {
          const uint4 pv = lds4(par + PAR_T2 + (hf * 8 + i) * 64 + tq * 16);
          x[2 * i] = hfma2(hfma2(ln_norm(x[2 * i], mm0, ih0, il0), pv.x, pv.y), pv.z, x[2 * i]);
          x[2 * i + 1] = hfma2(hfma2(ln_norm(x[2 * i + 1], mm1, ih1, il1), pv.x, pv.y), pv.z, x[2 * i + 1]);
        }
#pragma unroll
        for (int i = 0; i < 8; i += 2) stmatrix4((trow ^ (i << 4)) + hf * 16384, x[2 * i], x[2 * i + 1], x[2 * i + 2], x[2 * i + 3]);
        if (!cand) fence_async_smem();
        __syncwarp();
        if (!cand && elect_one()) {
          tma2d_store(&maps.out, res + hf * 16384 + warp * 2048, cj * 128 + hf * 64, rb * 128 + warp * 16);
          asm volatile("cp.async.bulk.commit_group;" ::: "memory");
        }
      }
    }
    if (cand) {
      const int wrow0 = warp * 16;
#pragma unroll 2
      for (int p = 0; p < 8; p++) {
        const int row = 2 * p + (ln >> 4), ch = ln & 15;
        const uint4 v = lds4(res + (ch >> 3) * 16384 + (wrow0 + row) * 128 + (((ch & 7) ^ (row & 7)) << 4));
        if (rb * 128 + wrow0 + row != iwin) *reinterpret_cast<uint4*>(P.out + (size_t)(rb * 128 + wrow0 + row) * DM + cj * 128 + ch * 8) = v;
      }
    }
    asm volatile("cp.async.bulk.wait_group.read 0;" ::: "memory");
    PROF(8, ct == PT, 11); STAMP(15);
    cluster_wait();
  }
}

typedef CUresult (*EncodeFn)(CUtensorMap*, CUtensorMapDataType, cuuint32_t, void*, const cuuint64_t*, const cuuint64_t*,
                             const cuuint32_t*, const cuuint32_t*, CUtensorMapInterleave, CUtensorMapSwizzle,
                             CUtensorMapL2promotion, CUtensorMapFloatOOBfill);

void map2d(EncodeFn enc, CUtensorMap* m, const void* p, uint64_t rows, uint64_t cols, uint32_t brows) {
  cuuint64_t dims[2] = {cols, rows}, strides[1] = {cols * 2};
  cuuint32_t box[2] = {64, brows}, es[2] = {1, 1};
  enc(m, CU_TENSOR_MAP_DATA_TYPE_BFLOAT16, 2, const_cast<void*>(p), dims, strides, box, es, CU_TENSOR_MAP_INTERLEAVE_NONE,
      CU_TENSOR_MAP_SWIZZLE_128B, CU_TENSOR_MAP_L2_PROMOTION_L2_256B, CU_TENSOR_MAP_FLOAT_OOB_FILL_NONE);
}
void map2d_narrow(EncodeFn enc, CUtensorMap* m, const void* p, uint64_t rows, uint64_t cols, uint32_t brows) {
  cuuint64_t dims[2] = {cols, rows}, strides[1] = {cols * 2};
  cuuint32_t box[2] = {32, brows}, es[2] = {1, 1};
  enc(m, CU_TENSOR_MAP_DATA_TYPE_BFLOAT16, 2, const_cast<void*>(p), dims, strides, box, es, CU_TENSOR_MAP_INTERLEAVE_NONE,
      CU_TENSOR_MAP_SWIZZLE_64B, CU_TENSOR_MAP_L2_PROMOTION_L2_64B, CU_TENSOR_MAP_FLOAT_OOB_FILL_NONE);
}
void map3d(EncodeFn enc, CUtensorMap* m, const void* p, uint64_t rows, uint64_t cols, uint32_t brows, uint32_t nch) {
  cuuint64_t dims[3] = {64, rows, cols / 64}, strides[2] = {cols * 2, 128};
  cuuint32_t box[3] = {64, brows, nch}, es[3] = {1, 1, 1};
  enc(m, CU_TENSOR_MAP_DATA_TYPE_BFLOAT16, 3, const_cast<void*>(p), dims, strides, box, es, CU_TENSOR_MAP_INTERLEAVE_NONE,
      CU_TENSOR_MAP_SWIZZLE_128B, CU_TENSOR_MAP_L2_PROMOTION_L2_256B, CU_TENSOR_MAP_FLOAT_OOB_FILL_NONE);
}

}

extern "C" void kernel_launch(void* const* d_in, const int* in_sizes, int n_in, void* d_out, int out_size) {
  (void)in_sizes; (void)n_in; (void)out_size;
  static EncodeFn enc = nullptr;
  if (!enc) {
    void* fn = nullptr;
    cudaDriverEntryPointQueryResult st;
    cudaGetDriverEntryPoint("cuTensorMapEncodeTiled", &fn, cudaEnableDefault, &st);
    enc = (EncodeFn)fn;
    cudaFuncSetAttribute(fused_kernel, cudaFuncAttributeMaxDynamicSharedMemorySize, SMEM_BYTES);
  }
  Maps maps;
  map2d(enc, &maps.x, d_in[0], SEQ, DM, 128);
  map2d(enc, &maps.out, d_out, SEQ, DM, 16);
  map3d(enc, &maps.wq, d_in[3], DM, NQ, 64, 2);
  map3d(enc, &maps.k, d_in[1], 4 * SK, 128, 128, 1);
  map3d(enc, &maps.v, d_in[2], 4 * SK, 128, 128, 1);
  map3d(enc, &maps.wo, d_in[4], NQ, DM, 64, 2);
  map2d_narrow(enc, &maps.wg, d_in[7], DM, FF, 256);
  map2d_narrow(enc, &maps.wu, d_in[8], DM, FF, 256);
  map3d(enc, &maps.wd, d_in[9], FF, DM, 32, 4);
  map2d_narrow(enc, &maps.wm, d_in[11], DM, NMOD, 256);
  Ptrs p;
  p.x = (const __nv_bfloat16*)d_in[0];
  p.w_r = (const __nv_bfloat16*)d_in[6];
  p.w_gate = (const __nv_bfloat16*)d_in[7];
  p.w_up = (const __nv_bfloat16*)d_in[8];
  p.w_down = (const __nv_bfloat16*)d_in[9];
  p.c = (const __nv_bfloat16*)d_in[10];
  p.w_mod = (const __nv_bfloat16*)d_in[11];
  p.out = (__nv_bfloat16*)d_out;
  fused_kernel<<<NMAIN + NHELP, 384, SMEM_BYTES>>>(maps, p);
}
```

```cpp
#include <cuda_runtime.h>
#include <cuda_bf16.h>
#include <cuda.h>
#include <stdint.h>
#include <type_traits>

#define HD 2
#define HDX 2
#define NRS 8
#define OSL 900
#define OSL2 400
#define RSL 40
#define BIAS 96.f
#define GL 1
#define N1L 1
#define VREL 5
#define OPS 8192
#define ODS1 5
#define ODS 7
#define PG0 15
#define WB 2
#define WN 20
#define HU 32
#define RES0 17
#define RES1 20
#define GOST 20
#define NS1 5
#define LD2 4
#define FPACE0 2
#define FPACE 3
#define CR 8
#define CS 8

namespace {

constexpr int SEQ = 2048, DM = 1024, NQ = 4096, SK = 2048, WIN = 512, FF = 3584, NMOD = 6144;
constexpr int NMAIN = 128, NHELP = 4, NFFN = 112;
constexpr int NSLOT = 4, SLOT_BYTES = 32768, UNIT = 16384, GST_BYTES = 3 * UNIT;
constexpr uint32_t XT1 = 0xDCBA, XT2 = 0x9687;
constexpr uint32_t WT0 = 0xA741, WT1 = 0x7420, WT2 = 0x4A20;
constexpr uint32_t AT0 = WT1, AT1 = WT2;
constexpr uint32_t QT = 0xDC9696DC;
constexpr int OFF_STAGE = 12 * UNIT;
constexpr uint32_t FT_G = 0x07B3, FT_U = 0xA628, FT_D = 0x5149;
constexpr int OFF_RES = 12 * UNIT;
constexpr int OFF_PAR = 14 * UNIT;
constexpr int OFF_BAR = OFF_PAR + 2528;
constexpr int SMEM_BYTES = OFF_BAR + 544;
static_assert(SMEM_BYTES <= 232448, "smem");

constexpr int PAR_T1 = 0;
constexpr int PAR_T2 = 512;
constexpr int PAR_CONST = 1536;
constexpr int PAR_RED = 1600;
constexpr int PAR_SINK = 2176;

struct Maps {
  CUtensorMap x, wq, k, v, wo, wg, wu, wd, wm, out;
};
struct Ptrs {
  const __nv_bfloat16 *x, *w_r, *c, *w_mod, *w_gate, *w_up, *w_down;
  __nv_bfloat16* out;
};

__device__ __align__(1024) uint8_t g_act[16 * 80 * UNIT];
__device__ __align__(128) uint32_t g_mod[NMOD];
__device__ __align__(128) uint32_t g_modp[2 * 2 * DM];
__device__ __align__(128) uint32_t g_ln1[SEQ * 4];
__device__ __align__(128) uint32_t g_cnt_h[16 * 32];
__device__ __align__(128) uint32_t g_cnt_o[128 * 32];
__device__ __align__(128) uint32_t g_xch[NMAIN * 8 * 256 * 4];
__device__ __align__(128) uint32_t g_stats[8 * SEQ * 4];
__device__ __align__(128) uint32_t g_cand[CR * 512];
__device__ __align__(128) uint32_t g_row[16 * 2 * DM];
__device__ __align__(128) uint32_t g_ypart[NMAIN * NFFN * 4];
__device__ __forceinline__ uint32_t* ypart_slot(int writer, int reader) { return g_ypart + (writer * NMAIN + reader) * 4; }
__device__ uint32_t g_epoch;

__device__ __forceinline__ uint32_t fresh_lane() { uint32_t l; asm volatile("mov.u32 %0, %%laneid;" : "=r"(l)); return l; }
__device__ __forceinline__ uint32_t frag_offset(int warp) {
  const uint32_t l = fresh_lane();
  return ((warp & 3) * 16 + (l & 15)) * 128 + (((l >> 4) ^ (l & 7)) << 4);
}
__device__ __forceinline__ bool elect_one() {
  uint32_t p;
  asm volatile("{ .reg .pred q; elect.sync _|q, 0xffffffff; selp.u32 %0, 1, 0, q; }" : "=r"(p));
  return p;
}
__device__ __forceinline__ uint32_t smem_u32(const void* p) { return (uint32_t)__cvta_generic_to_shared(p); }
__device__ __forceinline__ void mbar_init(uint32_t bar, uint32_t cnt) {
  asm volatile("mbarrier.init.shared::cta.b64 [%0], %1;" ::"r"(bar), "r"(cnt) : "memory");
}
__device__ __forceinline__ void mbar_expect_tx(uint32_t bar, uint32_t bytes) {
  asm volatile("mbarrier.arrive.expect_tx.shared::cta.b64 _, [%0], %1;" ::"r"(bar), "r"(bytes) : "memory");
}
__device__ __forceinline__ void mbar_arrive(uint32_t bar) {
  asm volatile("mbarrier.arrive.shared::cta.b64 _, [%0];" ::"r"(bar) : "memory");
}
__device__ __forceinline__ void mbar_arrive_pred(uint32_t bar, bool p) {
  asm volatile("{ .reg .pred p; setp.ne.b32 p, %1, 0; @p mbarrier.arrive.shared::cta.b64 _, [%0]; }" ::"r"(bar), "r"((int)p) : "memory");
}
__device__ __forceinline__ void mbar_arrive_cl(uint32_t bar, uint32_t off, bool p = true) {
  asm volatile("{ .reg .pred p, q; .reg .b32 a; setp.ne.b32 q, %2, 0; setp.ne.and.b32 p, %0, 0, q; add.u32 a, %0, %1; @p mbarrier.arrive.shared::cluster.b64 _, [a]; }"
               ::"r"(bar), "r"(off), "r"((int)p) : "memory");
}
__device__ __forceinline__ uint32_t mapa(uint32_t addr, uint32_t cta) {
  uint32_t r; asm("mapa.shared::cluster.u32 %0, %1, %2;" : "=r"(r) : "r"(addr), "r"(cta)); return r;
}
__device__ __forceinline__ void cluster_arrive() { asm volatile("barrier.cluster.arrive.relaxed.aligned;" ::: "memory"); }
__device__ __forceinline__ void cluster_wait() { asm volatile("barrier.cluster.wait.aligned;" ::: "memory"); }
__device__ __forceinline__ void watchdog(uint32_t& n) {
}
__device__ __forceinline__ void mbar_wait(uint32_t bar, uint32_t parity) {
  asm volatile("{\n.reg .pred p;\nWAIT_%=:\nmbarrier.try_wait.parity.shared::cta.b64 p, [%0], %1;\n@!p bra WAIT_%=;\n}" ::"r"(bar), "r"(parity) : "memory");
}
__device__ __forceinline__ bool mbar_test(uint32_t bar, uint32_t parity) {
  uint32_t ok;
  asm volatile("{\n.reg .pred p;\nmbarrier.test_wait.parity.shared::cta.b64 p, [%1], %2;\nselp.u32 %0, 1, 0, p;\n}" : "=r"(ok) : "r"(bar), "r"(parity) : "memory");
  return ok;
}
__device__ __forceinline__ uint64_t l2_stream() {
  uint64_t f; asm("createpolicy.fractional.L2::evict_first.b64 %0, 1.0;" : "=l"(f)); return f;
}
__device__ __forceinline__ uint64_t l2_normal() {
  uint64_t f; asm("createpolicy.fractional.L2::evict_normal.b64 %0, 1.0;" : "=l"(f)); return f;
}
__device__ __forceinline__ void tma2d(uint32_t dst, const CUtensorMap* m, int c0, int c1, uint32_t bar) {
  asm volatile("cp.async.bulk.tensor.2d.shared::cluster.global.mbarrier::complete_tx::bytes.L2::cache_hint [%0], [%1, {%3, %4}], [%2], %5;"
               ::"r"(dst), "l"(m), "r"(bar), "r"(c0), "r"(c1), "l"(l2_stream()) : "memory");
}
__device__ __forceinline__ void bulk_load(uint32_t dst, const void* src, uint32_t bytes, uint32_t bar) {
  asm volatile("cp.async.bulk.shared::cluster.global.mbarrier::complete_tx::bytes [%0], [%1], %2, [%3];" ::"r"(dst), "l"(src), "r"(bytes), "r"(bar) : "memory");
}
__device__ __forceinline__ void bulk_load_stream(uint32_t dst, const void* src, uint32_t bytes, uint32_t bar, uint64_t pol = l2_stream()) {
  asm volatile("cp.async.bulk.shared::cluster.global.mbarrier::complete_tx::bytes.L2::cache_hint [%0], [%1], %2, [%3], %4;"
               ::"r"(dst), "l"(src), "r"(bytes), "r"(bar), "l"(pol) : "memory");
}
__device__ __forceinline__ void tma2d_store(const CUtensorMap* m, uint32_t src, int c0, int c1) {
  asm volatile("cp.async.bulk.tensor.2d.global.shared::cta.bulk_group [%0, {%2, %3}], [%1];" ::"l"(m), "r"(src), "r"(c0), "r"(c1) : "memory");
}
__device__ __forceinline__ void bulk_store(void* dst, uint32_t src, uint32_t bytes) {
  asm volatile("cp.async.bulk.global.shared::cta.bulk_group [%0], [%1], %2;" ::"l"(dst), "r"(src), "r"(bytes) : "memory");
}
__device__ __forceinline__ int slice_of(int i) { return i + ((i & 7) == 1) - ((i & 7) == 2); }
__device__ __forceinline__ uint32_t unit_of(uint32_t table, uint32_t i) { return ((table >> (i * 4)) & 15) * UNIT; }
__device__ __forceinline__ void tma3d(uint32_t dst, const CUtensorMap* m, int c0, int c1, int c2, uint32_t bar) {
  asm volatile("cp.async.bulk.tensor.3d.shared::cluster.global.mbarrier::complete_tx::bytes.L2::cache_hint [%0], [%1, {%3, %4, %5}], [%2], %6;"
               ::"r"(dst), "l"(m), "r"(bar), "r"(c0), "r"(c1), "r"(c2), "l"(l2_stream()) : "memory");
}
template <bool STREAM>
__device__ __forceinline__ void tma3d_mc(uint32_t dst, const CUtensorMap* m, int c0, int c1, int c2, uint32_t bar) {
  if (STREAM)
    asm volatile("cp.async.bulk.tensor.3d.shared::cluster.global.mbarrier::complete_tx::bytes.multicast::cluster.L2::cache_hint [%0], [%1, {%3, %4, %5}], [%2], %6, %7;"
                 ::"r"(dst), "l"(m), "r"(bar), "r"(c0), "r"(c1), "r"(c2), "h"((uint16_t)3), "l"(l2_stream()) : "memory");
  else
    asm volatile("cp.async.bulk.tensor.3d.shared::cluster.global.mbarrier::complete_tx::bytes.multicast::cluster [%0], [%1, {%3, %4, %5}], [%2], %6;"
                 ::"r"(dst), "l"(m), "r"(bar), "r"(c0), "r"(c1), "r"(c2), "h"((uint16_t)3) : "memory");
}
__device__ __forceinline__ void prefetch_map(const CUtensorMap* m) {
  asm volatile("prefetch.tensormap [%0];" ::"l"(m) : "memory");
}
__device__ __forceinline__ void fence_async() { asm volatile("fence.proxy.async.global;" ::: "memory"); }
__device__ __forceinline__ void fence_async_smem() { asm volatile("fence.proxy.async.shared::cta;" ::: "memory"); }
__device__ __forceinline__ void bar_sync(int id, int n) { asm volatile("bar.sync %0, %1;" ::"r"(id), "r"(n) : "memory"); }
__device__ __forceinline__ void bar_arrive(int id, int n) { asm volatile("bar.arrive %0, %1;" ::"r"(id), "r"(n) : "memory"); }
__device__ __forceinline__ void wg_fence() { asm volatile("wgmma.fence.sync.aligned;" ::: "memory"); }
__device__ __forceinline__ void wg_commit() { asm volatile("wgmma.commit_group.sync.aligned;" ::: "memory"); }
template <int N> __device__ __forceinline__ void wg_wait() { asm volatile("wgmma.wait_group.sync.aligned %0;" ::"n"(N) : "memory"); }
__device__ __forceinline__ uint64_t make_desc(uint32_t addr, uint32_t lbo, uint32_t sbo) {
  return (uint64_t)((addr & 0x3FFFF) >> 4) | ((uint64_t)(lbo >> 4) << 16) | ((uint64_t)(sbo >> 4) << 32) | (1ull << 62);
}
__device__ __forceinline__ uint32_t ld_relaxed(const uint32_t* p) {
  uint32_t v; asm volatile("ld.relaxed.gpu.global.u32 %0, [%1];" : "=r"(v) : "l"(p) : "memory"); return v;
}
__device__ __forceinline__ uint32_t ld_acquire(const uint32_t* p) {
  uint32_t v; asm volatile("ld.acquire.gpu.global.u32 %0, [%1];" : "=r"(v) : "l"(p) : "memory"); return v;
}
__device__ __forceinline__ uint4 ld_relaxed4(const uint32_t* p) {
  uint4 v; asm volatile("ld.relaxed.gpu.global.v4.u32 {%0,%1,%2,%3}, [%4];" : "=r"(v.x), "=r"(v.y), "=r"(v.z), "=r"(v.w) : "l"(p) : "memory"); return v;
}
__device__ __forceinline__ void st_relaxed(uint32_t* p, uint32_t v) {
  asm volatile("st.relaxed.gpu.global.u32 [%0], %1;" ::"l"(p), "r"(v) : "memory");
}
__device__ __forceinline__ void st_relaxed4(uint32_t* p, uint32_t a, uint32_t b, uint32_t c, uint32_t d) {
  asm volatile("st.relaxed.gpu.global.v4.u32 [%0], {%1,%2,%3,%4};" ::"l"(p), "r"(a), "r"(b), "r"(c), "r"(d) : "memory");
}
__device__ __forceinline__ void st_b128(uint32_t* p, uint32_t a, uint32_t b, uint32_t c, uint32_t d) {
  asm volatile("{ .reg .b64 u, v; .reg .b128 w; mov.b64 u, {%1, %2}; mov.b64 v, {%3, %4}; mov.b128 w, {u, v}; st.relaxed.gpu.global.b128 [%0], w; }"
               ::"l"(p), "r"(a), "r"(b), "r"(c), "r"(d) : "memory");
}
__device__ __forceinline__ uint4 ld_b128(const uint32_t* p) {
  uint4 r;
  asm volatile("{ .reg .b64 u, v; .reg .b128 w; ld.relaxed.gpu.global.b128 w, [%4]; mov.b128 {u, v}, w; mov.b64 {%0, %1}, u; mov.b64 {%2, %3}, v; }"
               : "=r"(r.x), "=r"(r.y), "=r"(r.z), "=r"(r.w) : "l"(p) : "memory");
  return r;
}
__device__ __forceinline__ void st_pairs(uint32_t* p, uint32_t a, uint32_t b, uint32_t tag) {
  asm volatile("{ .reg .b64 u, v; mov.b64 u, {%1, %3}; mov.b64 v, {%2, %3}; st.relaxed.gpu.global.v2.b64 [%0], {u, v}; }"
               ::"l"(p), "r"(a), "r"(b), "r"(tag) : "memory");
}
__device__ __forceinline__ uint4 ld_pairs(const uint32_t* p) {
  uint4 v;
  asm volatile("{ .reg .b64 u, v; ld.relaxed.gpu.global.v2.b64 {u, v}, [%4]; mov.b64 {%0, %1}, u; mov.b64 {%2, %3}, v; }"
               : "=r"(v.x), "=r"(v.y), "=r"(v.z), "=r"(v.w) : "l"(p) : "memory");
  return v;
}
__device__ __forceinline__ uint2 ld_pair(const uint32_t* p) {
  uint2 v;
  asm volatile("{ .reg .b64 u; ld.relaxed.gpu.global.b64 u, [%2]; mov.b64 {%0, %1}, u; }" : "=r"(v.x), "=r"(v.y) : "l"(p) : "memory");
  return v;
}
__device__ __forceinline__ void red_release(uint32_t* p, uint32_t v) {
  asm volatile("red.release.gpu.global.add.u32 [%0], %1;" ::"l"(p), "r"(v) : "memory");
}
__device__ __forceinline__ uint32_t ldg_nc1(const void* p) {
  uint32_t v;
  asm volatile("ld.global.nc.u32 %0, [%1];" : "=r"(v) : "l"(p));
  return v;
}
__device__ __forceinline__ uint4 ldg_nc4(const void* p) {
  uint4 v; asm volatile("ld.global.nc.L1::no_allocate.v4.u32 {%0,%1,%2,%3}, [%4];" : "=r"(v.x), "=r"(v.y), "=r"(v.z), "=r"(v.w) : "l"(p)); return v;
}
__device__ __forceinline__ uint4 ldg_stream4(const void* p) {
  uint4 v;
  asm volatile("ld.global.nc.L1::no_allocate.L2::cache_hint.v4.u32 {%0,%1,%2,%3}, [%4], %5;" : "=r"(v.x), "=r"(v.y), "=r"(v.z), "=r"(v.w) : "l"(p), "l"(l2_stream()));
  return v;
}
__device__ __forceinline__ void stg4(void* p, uint4 v) {
  asm volatile("st.global.v4.u32 [%0], {%1,%2,%3,%4};" ::"l"(p), "r"(v.x), "r"(v.y), "r"(v.z), "r"(v.w) : "memory");
}
__device__ __forceinline__ void wait_counter(const uint32_t* p, uint32_t target) {
  uint32_t n = 0;
  while (__any_sync(0xffffffffu, (int)(ld_acquire(p) - target) < 0)) { watchdog(n); }
}
__device__ __forceinline__ uint32_t tagf(float v, uint32_t tag) { return (__float_as_uint(v) & ~3u) | tag; }
__device__ __forceinline__ bool tag_ok(uint4 v, uint32_t tag) { return (((v.x ^ tag) | (v.y ^ tag) | (v.z ^ tag) | (v.w ^ tag)) & 3u) == 0; }
__device__ __forceinline__ float untag_sum(uint32_t a, uint32_t b) { return __uint_as_float(a & ~3u) + __uint_as_float(b & ~3u); }
__device__ __forceinline__ uint4 poll4(const uint32_t* p, uint32_t tag) {
  uint4 v = ld_relaxed4(p);
  uint32_t n = 0;
  while (!__all_sync(0xffffffffu, tag_ok(v, tag))) { v = ld_relaxed4(p); watchdog(n); }
  return v;
}
__device__ __forceinline__ float bf_lo(uint32_t v) { return __uint_as_float(v << 16); }
__device__ __forceinline__ float bf_hi(uint32_t v) { return __uint_as_float(v & 0xffff0000u); }
__device__ __forceinline__ uint32_t pack_bf(float lo, float hi) {
  uint32_t r; asm("cvt.rn.bf16x2.f32 %0, %1, %2;" : "=r"(r) : "f"(hi), "f"(lo)); return r;
}
__device__ __forceinline__ float rbf(float v) { return __uint_as_float(pack_bf(0.f, v) & 0xffff0000u); }
__device__ __forceinline__ uint32_t hmul2(uint32_t a, uint32_t b) {
  uint32_t r; asm("mul.rn.bf16x2 %0, %1, %2;" : "=r"(r) : "r"(a), "r"(b)); return r;
}
__device__ __forceinline__ uint32_t hadd2(uint32_t a, uint32_t b) {
  uint32_t r; asm("add.rn.bf16x2 %0, %1, %2;" : "=r"(r) : "r"(a), "r"(b)); return r;
}
__device__ __forceinline__ uint32_t hsub2(uint32_t a, uint32_t b) {
  uint32_t r; asm("sub.rn.bf16x2 %0, %1, %2;" : "=r"(r) : "r"(a), "r"(b)); return r;
}
__device__ __forceinline__ float rcp(float x) { float r; asm("rcp.approx.ftz.f32 %0, %1;" : "=f"(r) : "f"(x)); return r; }
__device__ __forceinline__ float ex2(float x) { float r; asm("ex2.approx.ftz.f32 %0, %1;" : "=f"(r) : "f"(x)); return r; }
__device__ __forceinline__ void stmatrix4(uint32_t addr, uint32_t a, uint32_t b, uint32_t c, uint32_t d) {
  asm volatile("stmatrix.sync.aligned.m8n8.x4.shared.b16 [%0], {%1,%2,%3,%4};" ::"r"(addr), "r"(a), "r"(b), "r"(c), "r"(d) : "memory");
}
__device__ __forceinline__ void ldmatrix4(uint32_t addr, uint32_t& a, uint32_t& b, uint32_t& c, uint32_t& d) {
  asm volatile("ldmatrix.sync.aligned.m8n8.x4.shared.b16 {%0,%1,%2,%3}, [%4];" : "=r"(a), "=r"(b), "=r"(c), "=r"(d) : "r"(addr) : "memory");
}
__device__ __forceinline__ void ldmatrix4t(uint32_t addr, uint32_t& a, uint32_t& b, uint32_t& c, uint32_t& d) {
  asm volatile("ldmatrix.sync.aligned.m8n8.x4.trans.shared.b16 {%0,%1,%2,%3}, [%4];" : "=r"(a), "=r"(b), "=r"(c), "=r"(d) : "r"(addr) : "memory");
}
__device__ __forceinline__ void mma16816(float (&d)[4], uint32_t a0, uint32_t a1, uint32_t a2, uint32_t a3, uint32_t b0, uint32_t b1) {
  asm volatile("mma.sync.aligned.m16n8k16.row.col.f32.bf16.bf16.f32 {%0,%1,%2,%3}, {%4,%5,%6,%7}, {%8,%9}, {%0,%1,%2,%3};"
               : "+f"(d[0]), "+f"(d[1]), "+f"(d[2]), "+f"(d[3]) : "r"(a0), "r"(a1), "r"(a2), "r"(a3), "r"(b0), "r"(b1));
}
__device__ __forceinline__ void sts1(uint32_t a, uint32_t v) { asm volatile("st.shared.u32 [%0], %1;" ::"r"(a), "r"(v) : "memory"); }
__device__ __forceinline__ uint4 lds4(uint32_t a) {
  uint4 v; asm volatile("ld.shared.v4.u32 {%0,%1,%2,%3}, [%4];" : "=r"(v.x), "=r"(v.y), "=r"(v.z), "=r"(v.w) : "r"(a) : "memory"); return v;
}
__device__ __forceinline__ uint2 lds2(uint32_t a) {
  uint2 v; asm volatile("ld.shared.v2.u32 {%0,%1}, [%2];" : "=r"(v.x), "=r"(v.y) : "r"(a) : "memory"); return v;
}
__device__ __forceinline__ uint32_t lds1(uint32_t a) {
  uint32_t v; asm volatile("ld.shared.u32 %0, [%1];" : "=r"(v) : "r"(a) : "memory"); return v;
}
__device__ __forceinline__ void sts2(uint32_t a, uint32_t x, uint32_t y) { asm volatile("st.shared.v2.u32 [%0], {%1,%2};" ::"r"(a), "r"(x), "r"(y) : "memory"); }
__device__ __forceinline__ void sts4(uint32_t a, uint4 v) {
  asm volatile("st.shared.v4.u32 [%0], {%1,%2,%3,%4};" ::"r"(a), "r"(v.x), "r"(v.y), "r"(v.z), "r"(v.w) : "memory");
}
__device__ __forceinline__ float silu_f(float v) { return __fdividef(v, 1.f + __expf(-v)); }
__device__ __forceinline__ uint32_t hfma2(uint32_t a, uint32_t b, uint32_t c) {
  uint32_t r; asm("fma.rn.bf16x2 %0, %1, %2, %3;" : "=r"(r) : "r"(a), "r"(b), "r"(c)); return r;
}
__device__ __forceinline__ void split_inv(float sd, uint32_t& ih, uint32_t& il) {
  const float inv = rcp(sd);
  ih = pack_bf(inv, inv);
  const float lo = inv - bf_lo(ih);
  il = pack_bf(lo, lo);
}
__device__ __forceinline__ uint32_t ln_norm(uint32_t x, uint32_t mean2, uint32_t ih, uint32_t il) {
  const uint32_t d = hsub2(x, mean2);
  return hfma2(d, ih, hmul2(d, il));
}
__device__ __forceinline__ uint32_t ln_mod(uint32_t x, uint32_t mean2, uint32_t ih, uint32_t il, uint32_t c1, uint32_t sh) {
  return hadd2(hmul2(ln_norm(x, mean2, ih, il), c1), sh);
}

#define R8(a, i) "+f"(a[i]), "+f"(a[i + 1]), "+f"(a[i + 2]), "+f"(a[i + 3]), "+f"(a[i + 4]), "+f"(a[i + 5]), "+f"(a[i + 6]), "+f"(a[i + 7])
#define D64 "{%0,%1,%2,%3,%4,%5,%6,%7,%8,%9,%10,%11,%12,%13,%14,%15,%16,%17,%18,%19,%20,%21,%22,%23,%24,%25,%26,%27,%28,%29,%30,%31," \
            "%32,%33,%34,%35,%36,%37,%38,%39,%40,%41,%42,%43,%44,%45,%46,%47,%48,%49,%50,%51,%52,%53,%54,%55,%56,%57,%58,%59,%60,%61,%62,%63}"
template <int TB>
__device__ __forceinline__ void mma_ss(float (&d)[64], uint64_t da, uint64_t db, int sc) {
  asm volatile("{\n.reg .pred p;\nsetp.ne.b32 p, %66, 0;\n"
               "wgmma.mma_async.sync.aligned.m64n128k16.f32.bf16.bf16 " D64 ", %64, %65, p, 1, 1, 0, %67;\n}"
               : R8(d, 0), R8(d, 8), R8(d, 16), R8(d, 24), R8(d, 32), R8(d, 40), R8(d, 48), R8(d, 56)
               : "l"(da), "l"(db), "r"(sc), "n"(TB));
}
template <int TB>
__device__ __forceinline__ void mma_rs(float (&d)[64], uint32_t a0, uint32_t a1, uint32_t a2, uint32_t a3, uint64_t db, int sc) {
  asm volatile("{\n.reg .pred p;\nsetp.ne.b32 p, %69, 0;\n"
               "wgmma.mma_async.sync.aligned.m64n128k16.f32.bf16.bf16 " D64 ", {%64,%65,%66,%67}, %68, p, 1, 1, %70;\n}"
               : R8(d, 0), R8(d, 8), R8(d, 16), R8(d, 24), R8(d, 32), R8(d, 40), R8(d, 48), R8(d, 56)
               : "r"(a0), "r"(a1), "r"(a2), "r"(a3), "l"(db), "r"(sc), "n"(TB));
}
#define D128 "{%0,%1,%2,%3,%4,%5,%6,%7,%8,%9,%10,%11,%12,%13,%14,%15,%16,%17,%18,%19,%20,%21,%22,%23,%24,%25,%26,%27,%28,%29,%30,%31," \
             "%32,%33,%34,%35,%36,%37,%38,%39,%40,%41,%42,%43,%44,%45,%46,%47,%48,%49,%50,%51,%52,%53,%54,%55,%56,%57,%58,%59,%60,%61,%62,%63," \
             "%64,%65,%66,%67,%68,%69,%70,%71,%72,%73,%74,%75,%76,%77,%78,%79,%80,%81,%82,%83,%84,%85,%86,%87,%88,%89,%90,%91,%92,%93,%94,%95," \
             "%96,%97,%98,%99,%100,%101,%102,%103,%104,%105,%106,%107,%108,%109,%110,%111,%112,%113,%114,%115,%116,%117,%118,%119,%120,%121,%122,%123,%124,%125,%126,%127}"
#define R128(d, e) R8(d, 0), R8(d, 8), R8(d, 16), R8(d, 24), R8(d, 32), R8(d, 40), R8(d, 48), R8(d, 56), \
                   R8(e, 0), R8(e, 8), R8(e, 16), R8(e, 24), R8(e, 32), R8(e, 40), R8(e, 48), R8(e, 56)
__device__ __forceinline__ void mma256_ss(float (&d)[64], float (&e)[64], uint64_t da, uint64_t db, int sc) {
  asm volatile("{\n.reg .pred p;\nsetp.ne.b32 p, %130, 0;\n"
               "wgmma.mma_async.sync.aligned.m64n256k16.f32.bf16.bf16 " D128 ", %128, %129, p, 1, 1, 0, 1;\n}"
               : R128(d, e) : "l"(da), "l"(db), "r"(sc));
}
__device__ __forceinline__ void mma256_rs(float (&d)[64], float (&e)[64], uint32_t a0, uint32_t a1, uint32_t a2, uint32_t a3, uint64_t db) {
  asm volatile("{\n.reg .pred p;\nsetp.ne.b32 p, 1, 0;\n"
               "wgmma.mma_async.sync.aligned.m64n256k16.f32.bf16.bf16 " D128 ", {%128,%129,%130,%131}, %132, p, 1, 1, 1;\n}"
               : R128(d, e) : "r"(a0), "r"(a1), "r"(a2), "r"(a3), "l"(db));
}
template <int N> __device__ __forceinline__ void keep(float (&a)[N]) {
#pragma unroll
  for (int i = 0; i < N; i++) asm volatile("" : "+f"(a[i])::"memory");
}
template <int N> __device__ __forceinline__ void keep(uint32_t (&a)[N]) {
#pragma unroll
  for (int i = 0; i < N; i++) asm volatile("" : "+r"(a[i])::"memory");
}

#define STAMP(idx) do {} while (0)
#define PROF(grp, cond, idx) do {} while (0)

constexpr float SCL2 = 1.4426950408889634f * 0.08838834764831845f;

__device__ __forceinline__ void pack_p(const float (&s)[64], uint32_t (&p)[32]) {
#pragma unroll
  for (int i = 0; i < 32; i++) p[i] = pack_bf(s[2 * i], s[2 * i + 1]);
}

__device__ __forceinline__ void issue_qk(float (&s)[64], uint32_t q0, uint32_t q1, uint32_t kslot) {
  const uint64_t db = make_desc(kslot, 16, 1024), da0 = make_desc(q0, 16, 1024), da1 = make_desc(q1, 16, 1024);
#pragma unroll
  for (int kk = 0; kk < 8; kk++) mma_ss<0>(s, (kk < 4 ? da0 : da1) + (kk & 3) * 2, db + (kk >> 2) * 1024 + (kk & 3) * 2, kk != 0);
}
__device__ __forceinline__ void issue_pv(float (&o)[64], uint32_t (&p)[32], uint32_t vslot, int acc) {
  uint64_t db = make_desc(vslot, 16384, 1024);
#pragma unroll
  for (int kk = 0; kk < 8; kk++)
    mma_rs<1>(o, p[4 * kk], p[4 * kk + 1], p[4 * kk + 2], p[4 * kk + 3], db + kk * 128, kk == 0 ? acc : 1);
}

template <int H>
__device__ __forceinline__ void store_chunk(const float (&a)[64], uint32_t addr) {
#pragma unroll
  for (int i = 8 * H; i < 8 * H + 8; i += 2)
    stmatrix4(addr ^ ((i & 7) << 4), pack_bf(a[4 * i], a[4 * i + 1]), pack_bf(a[4 * i + 2], a[4 * i + 3]),
              pack_bf(a[4 * i + 4], a[4 * i + 5]), pack_bf(a[4 * i + 6], a[4 * i + 7]));
}
template <int H>
__device__ __forceinline__ void store_chunk(const float (&a)[64], float i0, float i1, uint32_t addr) {
#pragma unroll
  for (int i = 8 * H; i < 8 * H + 8; i += 2)
    stmatrix4(addr ^ ((i & 7) << 4), pack_bf(a[4 * i] * i0, a[4 * i + 1] * i0), pack_bf(a[4 * i + 2] * i1, a[4 * i + 3] * i1),
              pack_bf(a[4 * i + 4] * i0, a[4 * i + 5] * i0), pack_bf(a[4 * i + 6] * i1, a[4 * i + 7] * i1));
}
__device__ __forceinline__ float inv_quad_sum(float l) {
  l += __shfl_xor_sync(0xffffffffu, l, 1);
  l += __shfl_xor_sync(0xffffffffu, l, 2);
  return rcp(l);
}

__device__ __forceinline__ void write_table(uint32_t table, bool ca, uint32_t t, const uint4& m0, const uint4& m1) {
  float c0 = untag_sum(m0.x, m1.x), c1 = untag_sum(m0.y, m1.y), c2 = untag_sum(m0.z, m1.z), c3 = untag_sum(m0.w, m1.w);
  if (ca) { c0 = 1.f + rbf(c0); c1 = 1.f + rbf(c1); c2 = 1.f + rbf(c2); c3 = 1.f + rbf(c3); }
  const uint32_t d = table + (t >> 2) * 64 + (t & 1) * 32 + (t & 2) * 2 + (ca ? 0 : 8);
  sts1(d, pack_bf(c0, c1));
  sts1(d + 16, pack_bf(c2, c3));
}

__device__ __forceinline__ void ln_scalars(float mean, float var, float& mb, float& sd) {
  mb = rbf(mean);
  float r; asm("sqrt.approx.ftz.f32 %0, %1;" : "=f"(r) : "f"(rbf(rbf(var) + 1e-5f)));
  sd = rbf(r);
}

__global__ void __cluster_dims__(2, 1, 1) __launch_bounds__(384, 1) fused_kernel(const __grid_constant__ Maps maps, const Ptrs P) {
  extern __shared__ __align__(1024) uint8_t smem_raw[];
  const uint32_t base = smem_u32(smem_raw);
  const int tid = threadIdx.x, lane = tid & 31;
  const int warp = __shfl_sync(0xffffffffu, tid >> 5, 0);
  int b = blockIdx.x;
  if (b < NMAIN) {
    const int p = b >> 1;
    const int grp = p < 4 ? 7 : (p < 36 ? (p + 2) & 7 : (p - 30) % 7), k = p < 4 ? 4 + p : (p < 36 ? (p - 4) >> 3 : 4 + (p - 36) / 7);
    b = grp << 4 | k << 1 | (b & 1);
  }
  PROF(31, tid == 0, 0);

  if (b >= NMAIN) {
    float* sc = reinterpret_cast<float*>(smem_raw);
    float* red = sc + DM;
    for (int k = tid; k < DM; k += 384) sc[k] = rbf(silu_f(__bfloat162float(P.c[k])));
    __syncthreads();
    if (tid < 256) {
      const int col = 2048 + (b - NMAIN) * 1024 + (tid & 127) * 8, r0 = (tid >> 7) * 512;
      float acc[8];
#pragma unroll
      for (int e = 0; e < 8; e++) acc[e] = 0.f;
#pragma unroll 1
      for (int r = r0; r < r0 + 512; r += HU) {
        uint4 w[HU];
#pragma unroll
        for (int u = 0; u < HU; u++) w[u] = ldg_stream4(P.w_mod + (size_t)(r + u) * NMOD + col);
#pragma unroll
        for (int u = 0; u < HU; u++) {
          float s = sc[r + u];
          acc[0] += s * bf_lo(w[u].x); acc[1] += s * bf_hi(w[u].x); acc[2] += s * bf_lo(w[u].y); acc[3] += s * bf_hi(w[u].y);
          acc[4] += s * bf_lo(w[u].z); acc[5] += s * bf_hi(w[u].z); acc[6] += s * bf_lo(w[u].w); acc[7] += s * bf_hi(w[u].w);
        }
      }
      if (tid >= 128) {
#pragma unroll
        for (int e = 0; e < 8; e++) red[(tid & 127) * 8 + e] = acc[e];
      }
      const uint32_t tag = ld_relaxed(&g_epoch) % 3 + 1;
      bar_sync(1, 256);
      if (tid < 128) {
        uint32_t o[8];
#pragma unroll
        for (int e = 0; e < 8; e++) o[e] = __float_as_uint(rbf(acc[e] + red[tid * 8 + e])) | tag;
        st_relaxed4(g_mod + col, o[0], o[1], o[2], o[3]);
        st_relaxed4(g_mod + col + 4, o[4], o[5], o[6], o[7]);
        const uint4 wr = ldg_nc4(P.w_r + tid * 8);
        const uint32_t wv[4] = {wr.x, wr.y, wr.z, wr.w};
        float dsum = 0.f;
#pragma unroll
        for (int e = 0; e < 8; e++) {
          const float m = bf_hi(o[e]);
          dsum += (b == NMAIN + 2 ? rbf(1.f + m) : m) * ((e & 1) ? bf_hi(wv[e >> 1]) : bf_lo(wv[e >> 1]));
        }
#pragma unroll
        for (int k = 16; k > 0; k >>= 1) dsum += __shfl_xor_sync(0xffffffffu, dsum, k);
        if (lane == 0) st_relaxed(g_mod + (b - NMAIN) * 4 + warp, tagf(dsum, tag));
      }
    }
    PROF(2, tid == 0, 1);
    return;
  }

  const int rank = b & 1;
  const int rb = ((b >> 4) << 1) | rank, cj = (b >> 1) & 7;
  const bool late = b & 4;
  const uint32_t bfull = base + OFF_BAR, bempty = bfull + NSLOT * 8;
  const uint32_t gfull = bempty + NSLOT * 8, gempty = gfull + 32;
  const uint32_t bar_ofull = gempty + 32;
  const uint32_t bar_ofree = bar_ofull + 32;
  const uint32_t bar_par = bar_ofree + 32;
  const uint32_t bar_mod = bar_par + 8;
  const uint32_t bar_pread = bar_mod + 8;
  const uint32_t bar_xres = bar_pread + 8;
  const uint32_t bar_ring = bar_xres + 8;
  const uint32_t bar_box = bar_ring + 24;
  const uint32_t bar_go = bar_box + 96;
  const uint32_t bar_go2 = bar_go + 16;
  const uint32_t bar_cnt = bar_go + 24;
  const uint32_t xfull = bar_go + 40, xempty = xfull + 32;
  const uint32_t bar_hw = xempty + 32, bar_hx = bar_hw + 8;
  const uint32_t bar_hpub = bar_hx + 16;
  const uint32_t bar_win = bar_hpub + 16;
  const uint32_t bar_rx = bar_win + 8;
  const uint32_t bar_sel = bar_rx + 8;
  const uint32_t bar_gate = bar_sel + 8;
  const uint32_t bar_rel = bar_gate + 8;
  const uint32_t bar_od = bar_rel + 8;
  const uint32_t bar_mod2 = bar_od + 8;
  const uint32_t bar_res = bar_go + 8;
  const uint32_t stage = base + OFF_STAGE, par = base + OFF_PAR;

  if (warp == 10 && elect_one()) prefetch_map(&maps.wm);
  if (warp == 8 && elect_one()) {
    for (int s = 0; s < NSLOT; s++) { mbar_init(bfull + s * 8, 1); mbar_init(bempty + s * 8, 16); }
    for (int s = 0; s < 4; s++) { mbar_init(gfull + s * 8, 1); mbar_init(gempty + s * 8, 16); mbar_init(xfull + s * 8, 1); mbar_init(xempty + s * 8, 8); mbar_init(bar_ofree + s * 8, 1); mbar_init(bar_ofull + s * 8, 128); }
    mbar_init(bar_par, 64); mbar_init(bar_mod, 256); mbar_init(bar_pread, 2); mbar_init(bar_xres, 1);
    mbar_init(bar_ring, 8); mbar_init(bar_ring + 8, 8); mbar_init(bar_ring + 16, 8);
    mbar_init(bar_go, 1); mbar_init(bar_go2, 1); mbar_init(bar_cnt, 1); mbar_init(bar_cnt + 8, 1); mbar_init(bar_hpub, 8); mbar_init(bar_hpub + 8, 8); mbar_init(bar_res, 1); mbar_init(bar_win, 1); mbar_init(bar_rx, 1); mbar_init(bar_sel, 64); mbar_init(bar_gate, 8); mbar_init(bar_rel, 8); mbar_init(bar_od, 1); mbar_init(bar_mod2, 64);
    for (int s = 0; s < 12; s++) mbar_init(bar_box + s * 8, 1);
    asm volatile("fence.mbarrier_init.release.cluster;" ::: "memory");
    prefetch_map(&maps.x); prefetch_map(&maps.wq); prefetch_map(&maps.k); prefetch_map(&maps.v);
  }
  if (warp == 9 && elect_one()) {
    mbar_init(bar_hw, 1); mbar_init(bar_hx, 1); mbar_init(bar_hx + 8, 1);
    asm volatile("fence.mbarrier_init.release.cluster;" ::: "memory");
    mbar_expect_tx(bar_hw, 32768);
    mbar_expect_tx(bar_hx, 16384);
    mbar_expect_tx(bar_hx + 8, 16384);
    const __nv_bfloat16* xs = P.x + (size_t)(rb * 128 + cj * 16) * DM;
    bulk_load(base + 2 * GST_BYTES, xs, 16384, bar_hx);
    if (!late) {
      tma2d(stage, &maps.wm, (b >> 1) * 32, rank * 512, bar_hw);
      tma2d(stage + 16384, &maps.wm, (b >> 1) * 32, rank * 512 + 256, bar_hw);
    }
    bulk_load(base + 3 * GST_BYTES, xs + 8 * DM, 16384, bar_hx + 8);
  }
  cluster_arrive();

  if (warp >= 8) {
    asm volatile("setmaxnreg.dec.sync.aligned.u32 40;");
    if (warp < 10) bar_arrive(1, 320);
    const uint32_t epoch = ld_relaxed(&g_epoch);
    cluster_wait();
    if (warp == 8) {
      const int kvrow = (cj >> 1) * SK + (SK - WIN);
      int wch = cj * 8 + rank * 2;
#pragma unroll 1
      for (int ps = 0; ps < 3; ps++) {
        const CUtensorMap* mw = ps == 2 ? &maps.wo : &maps.wq;
        const uint32_t xt = ps == 1 ? XT1 : XT2, wt = ps == 0 ? WT0 : (ps == 1 ? WT1 : WT2);
        const int nst = ps == 2 ? 32 : 16;
#pragma unroll 1
        for (int i = 0; i < nst; i++) {
          const uint32_t bf = gfull + (i & 3) * 8;
          const int kt = ps == 2 ? (((cj & 1) * 4 + ((i >> 1) & 3)) * 4 + (i >> 3)) * 2 + (i & 1) : (ps ? i : slice_of(i) + (b & 14)) & 15;
          const uint32_t wd = base + unit_of(wt, i & 3) + rank * UNIT, xd = base + unit_of(xt, i & 3);
          const uint8_t* xs = g_act + (uint32_t)(rb * 80 + (ps - 1) * 16 + kt) * UNIT;
          if (ps == 0 && i == HD) mbar_wait(bar_mod, 0);
          if (ps == 2 && (i & 7) == 0 && i != 8) mbar_wait(i ? bar_cnt + i - 16 : bar_ofree + 24, 0);
          if ((i & 7) == 0) fence_async();
          if (i == RES0) mbar_wait(bar_res, 0);
          mbar_wait(bf, ((i >> 2) & 1) ^ 1);
          if (elect_one()) {
            mbar_expect_tx(bf, ps ? GST_BYTES : 2 * UNIT);
            if (ps && i < 2) bulk_load_stream(xd, xs, UNIT, bf);
            mbar_arrive_pred(bar_go, i == GOST);
            mbar_arrive_pred(bar_go2, ps == 1 && i == PG0);
            mbar_arrive_pred(bar_od, ps && i == (ps == 1 ? ODS1 : ODS) + 1);
            if (i == RES0) mbar_expect_tx(bar_xres, 32768);
          }
          const int wk = (i == 31 ? kt ^ (rank * 32) : kt) * 64, wc = i == 31 ? cj * 2 : wch;
          const uint64_t xp = i == 31 ? l2_normal() : l2_stream();
          mbar_wait(ps && i < 4 ? bempty + i * 8 : gempty + (i & 3) * 8, ((i >> 2) & 1) ^ 1);
          if (elect_one()) {
            tma3d_mc<true>(wd, mw, 0, wk, wc, bf);
            if (ps && i > 2) bulk_load_stream(xd, xs, UNIT, bf, xp);
            if (i == RES0 || i == RES1) tma2d(base + OFF_RES + (i == RES1) * UNIT, &maps.x, cj * 128 + (i == RES1) * 64, rb * 128, bar_xres);
          }
          if (ps && i == 2) {
            mbar_wait(bar_ofree + (ps - 1) * 16, 0);
            if (elect_one()) bulk_load_stream(xd, xs, UNIT, bf);
          }
        }
        if (ps == 2) break;
        wch = ps ? ((wch >> 3) ^ rank) * 2 : wch + 4;
#pragma unroll 1
        for (int u = 0; u < 16; u++) {
          const bool isk = (u == 0) || ((u & 1) && u < 15), kept = (0x1680 >> u) & 1;
          const int blk = (0x472FAD84u >> (u * 2)) & 3;
          const uint32_t sl = base + unit_of(ps ? AT1 : AT0, u & 3) + rank * UNIT, bf = bfull + (u & 3) * 8;
          mbar_wait(bf, ((u >> 2) & 1) ^ 1);
          if (!kept && elect_one()) mbar_expect_tx(bf, SLOT_BYTES);
          mbar_wait(u < 4 ? gempty + ((u + 1) >> 1) * 8 : bempty + (u & 3) * 8, ((u >> 2) & 1) ^ 1);
          if (elect_one()) {
            if (kept) mbar_arrive(bf);
            else if (ps && (blk >= 2 || u > 8)) tma3d_mc<true>(sl, isk ? &maps.k : &maps.v, 0, kvrow + blk * 128, rank, bf);
            else tma3d_mc<false>(sl, isk ? &maps.k : &maps.v, 0, kvrow + blk * 128, rank, bf);
          }
        }
      }
      if (elect_one()) mbar_expect_tx(bar_rx, UNIT);
      mbar_wait(bar_rel, 0);
      if (elect_one()) {
        bulk_load_stream(base + UNIT, g_act + (uint32_t)(rb * 80 + 16 + 63 - (cj & 1) * 32) * UNIT, UNIT, bar_rx);
      }
      if (b < NFFN) {
#pragma unroll 1
        for (int u = 0; u < 12; u++) {
          const uint32_t dst = base + unit_of(u < 4 ? FT_G : (u < 8 ? FT_U : FT_D), u & 3);
          if (elect_one()) mbar_expect_tx(bar_box + u * 8, UNIT);
          if (u == 0 || u == 2 || u == 8) mbar_wait(bar_ring + (u == 8 ? 16 : u * 4), 0);
          const int fp = u < 8 ? FPACE0 : FPACE;
          if (u >= fp) mbar_wait(bar_box + (u - fp) * 8, 0);
          if (elect_one()) {
            if (u < 8) tma2d(dst, u < 4 ? &maps.wg : &maps.wu, b * 32, (u & 3) * 256, bar_box + u * 8);
            else tma3d(dst, &maps.wd, 0, b * 32, (u - 8) * 4, bar_box + u * 8);
          }
        }
      }
    } else if (warp == 9) {
      const uint32_t target = 8 * (epoch + 1);
      uint32_t hmask = 0;
#pragma unroll 1
      for (int i = 0; i < 16; i++) {
        if (i == HDX) mbar_wait(bar_mod, 0);
        const int kt = (2 * cj + slice_of(i)) & 15;
        const uint32_t need = i == 15 ? 0xffffu : 1u << kt;
        if (i >= NRS && (hmask & need) != need) {
          uint32_t n = 0;
          do { hmask = __ballot_sync(0xffffffffu, ld_acquire(&g_cnt_h[rb * 32 + (lane & 15)]) == epoch + 1); watchdog(n); } while ((hmask & need) != need);
          PROF(1, lane == 0 && i == NRS, 26);
          fence_async();
        }
        mbar_wait(xempty + (i & 3) * 8, ((i >> 2) & 1) ^ 1);
        if (elect_one()) {
          mbar_expect_tx(xfull + (i & 3) * 8, UNIT);
          if (i < NRS) tma2d(base + (i & 3) * GST_BYTES, &maps.x, kt * 64, rb * 128, xfull + (i & 3) * 8);
          else bulk_load_stream(base + (i & 3) * GST_BYTES, g_act + (uint32_t)(rb * 80 + kt) * UNIT, UNIT, xfull + (i & 3) * 8);
        }
      }
      prefetch_map(&maps.wo);
#pragma unroll 1
      for (int t = 0; t < 4; t++) {
        if (t & 1) mbar_wait(bar_od, t >> 1);
        const int ops = OPS >> (t & 1);
#pragma unroll 1
        for (int p = 0; p < 32768; p += ops) {
          const uint32_t w = p >> 14, c = (p >> 13) & 1, off = w * 8192 + (p & 8191);
          mbar_wait(bar_ofull + (t & 1) * 16 + w * 8, t >> 1);
          if (elect_one()) {
            bulk_store(g_act + (uint32_t)(rb * 80 + 16 + (cj * 4 + t) * 2 + c) * UNIT + off, base + unit_of(QT, 2 * t + c) + off, ops);
            asm volatile("cp.async.bulk.commit_group;" ::: "memory");
            asm volatile("cp.async.bulk.wait_group.read 0;" ::: "memory");
          }
        }
        if (elect_one()) {
          mbar_arrive(t < 3 ? bar_ofree + t * 8 : bar_res);
          asm volatile("cp.async.bulk.wait_group 0;" ::: "memory");
          fence_async();
          red_release(&g_cnt_o[((rb * 4 + t) * 2 + (cj >> 2)) * 32], 2);
        }
        if (t) {
          wait_counter(&g_cnt_o[(rb * 8 + 2 * t + (cj & 1)) * 32], target);
          if (t & 1) wait_counter(&g_cnt_o[(rb * 8 + (t == 1 ? cj & 1 : 7 - (cj & 1))) * 32], target);
          if (elect_one()) mbar_arrive(t == 1 ? bar_ofree + 24 : bar_cnt + t * 8 - 16);
        }
      }
      PROF(2, lane == 0, 27);
      const uint32_t tag = epoch % 3 + 1;
      const uint32_t* inbox = g_cand + (b >> 4) % CR * 512 + (lane & 15) * CS;
      mbar_wait(bar_ring + 16, 0);
      uint32_t c0 = ld_relaxed(inbox), n = 0;
#define CAND_STEP(cv)                                                                                        \
      {                                                                                                      \
        const bool valid = (cv & 3u) == tag, all = __all_sync(0xffffffffu, valid);                           \
        const uint32_t best = __reduce_max_sync(0xffffffffu, valid ? cv : 0u);                               \
        const uint32_t blk = __ffs(__ballot_sync(0xffffffffu, cv == best)) - 1;                              \
        if (best) sts2(par + PAR_CONST + 56, best, (blk << 7 | (~best >> 2 & 127)) | (all ? 0x1800 : 0x800)); \
        if (all) break;                                                                                      \
        cv = ld_relaxed(inbox);                                                                              \
      }
      while (true) { CAND_STEP(c0) watchdog(n); }
    } else {
      const int t2 = tid - 320;
      if (late && warp == 10) {
        mbar_wait(bar_hx, 0);
        if (elect_one()) {
          tma2d(stage, &maps.wm, (b >> 1) * 32, rank * 512, bar_hw);
          tma2d(stage + 16384, &maps.wm, (b >> 1) * 32, rank * 512 + 256, bar_hw);
        }
      }
      {
        const uint32_t tag = epoch % 3 + 1;
        mbar_wait(bar_hx + 8, 0);
        mbar_wait(bar_hw, 0);
        __nanosleep(late ? OSL2 : OSL);
        {
          const uint32_t t7 = (warp & 1) * 64 + (lane >> 4) * 32 + 16 + (lane & 15);
          const uint32_t* pm = g_modp + ((cj * 128 + t7 * 4) & (DM - 1));
          uint4 m0, m1, m2, m3;
          uint32_t n = 0;
          do {
            m0 = ld_relaxed4(pm); m1 = ld_relaxed4(pm + 2 * DM); m2 = ld_relaxed4(pm + DM); m3 = ld_relaxed4(pm + 3 * DM);
            watchdog(n);
          } while (!__all_sync(0xffffffffu, tag_ok(m0, tag) && tag_ok(m1, tag) && tag_ok(m2, tag) && tag_ok(m3, tag)));
          write_table(par, false, t7, m0, m1);
          write_table(par, true, t7, m2, m3);
          mbar_arrive(bar_mod2);
        }
      }
      mbar_wait(bar_hpub + (warp & 1) * 8, 0);
      PROF(1, t2 == 0, 24);
#pragma unroll 1
      for (int c = 0; c < 8; c++) {
        const uint32_t off = (warp & 1) * UNIT + c * 2048 + lane * 16;
        uint8_t* dst = g_act + (uint32_t)(rb * 80 + cj * 2) * UNIT + off;
        const uint4 v0 = lds4(stage + off), v1 = lds4(stage + off + 512), v2 = lds4(stage + off + 1024), v3 = lds4(stage + off + 1536);
        stg4(dst, v0); stg4(dst + 512, v1); stg4(dst + 1024, v2); stg4(dst + 1536, v3);
      }
      __syncwarp();
      PROF(1, t2 == 0, 15);
      if (lane == 0) {
        mbar_arrive(bar_pread);
        red_release(&g_cnt_h[rb * 32 + cj * 2 + (warp & 1)], 1);
        PROF(1, t2 == 0, 25);
        prefetch_map(&maps.wg); prefetch_map(&maps.wu); prefetch_map(&maps.wd); prefetch_map(&maps.out);
      }
      __syncwarp();
      if (b < NFFN) {
        mbar_wait(bar_go2, 0);
        const __nv_bfloat16* pg = ((b & 1) ? P.w_up : P.w_gate) + (b >> 1) * 64 + (size_t)t2 * FF;
        const __nv_bfloat16* pd = P.w_down + (size_t)b * 32768 + t2 * 64;
        PROF(2, t2 == 0, 13);
#pragma unroll 1
        for (int i = 0; i < WN; i += WB) {
          uint32_t v[WB];
#pragma unroll
          for (int u = 0; u < WB; u++) {
            const int k = i + u;
            asm volatile("ld.global.cg.L2::128B.u32 %0, [%1];" : "=r"(v[u]) : "l"(k < 16 ? pg + (size_t)k * 64 * FF : pd + (k - 16) * 4096));
          }
#pragma unroll
          for (int u = 1; u < WB; u++) v[0] ^= v[u];
          sts1(par + PAR_SINK + t2 * 4, v[0]);
        }
        PROF(2, t2 == 0, 14);
      }
      const uint32_t tag = epoch % 3 + 1;
      mbar_wait(bar_go, 0);
      bar_sync(4, 64);
      if (warp == 10) {
        const uint32_t* src = g_mod + 2 * DM + cj * 128 + lane * 4;
        const uint2 wr = *reinterpret_cast<const uint2*>(P.w_r + cj * 128 + lane * 4);
        uint4 vga, vsb, vcb, vgb;
        uint32_t n = 0;
        do {
          vga = ld_relaxed4(src); vsb = ld_relaxed4(src + DM); vcb = ld_relaxed4(src + 2 * DM); vgb = ld_relaxed4(src + 3 * DM);
          watchdog(n);
        } while (!__all_sync(0xffffffffu, tag_ok(vga, tag) && tag_ok(vsb, tag) && tag_ok(vcb, tag) && tag_ok(vgb, tag)));
        const float c0 = rbf(1.f + bf_hi(vcb.x)), c1 = rbf(1.f + bf_hi(vcb.y)), c2 = rbf(1.f + bf_hi(vcb.z)), c3 = rbf(1.f + bf_hi(vcb.w));
        const float a0 = c0 * bf_lo(wr.x), a1 = c1 * bf_hi(wr.x), a2 = c2 * bf_lo(wr.y), a3 = c3 * bf_hi(wr.y);
        const uint32_t h0 = pack_bf(a0, a1), h1 = pack_bf(a2, a3);
        const uint32_t t1 = par + PAR_T1 + (lane >> 2) * 64 + (lane & 1) * 32 + (lane & 2) * 2;
        sts1(t1, h0); sts1(t1 + 8, pack_bf(a0 - bf_lo(h0), a1 - bf_hi(h0)));
        sts1(t1 + 16, h1); sts1(t1 + 24, pack_bf(a2 - bf_lo(h1), a3 - bf_hi(h1)));
        const uint32_t tg = par + PAR_SINK + (lane >> 3) * 64 + (lane & 1) * 32 + (lane & 6) * 2;
        sts1(tg, __byte_perm(vga.x, vga.y, 0x7632)); sts1(tg + 16, __byte_perm(vga.z, vga.w, 0x7632));
        sts4(par + PAR_T2 + lane * 32, make_uint4(pack_bf(c0, c1), __byte_perm(vsb.x, vsb.y, 0x7632), __byte_perm(vgb.x, vgb.y, 0x7632), __byte_perm(vga.x, vga.y, 0x7632)));
        sts4(par + PAR_T2 + lane * 32 + 16, make_uint4(pack_bf(c2, c3), __byte_perm(vsb.z, vsb.w, 0x7632), __byte_perm(vgb.z, vgb.w, 0x7632), __byte_perm(vga.z, vga.w, 0x7632)));
      } else {
        const uint4 g = poll4((lane & 8) ? g_mod + 8 - (lane & 1) * 4 : g_mod + 5 * DM + (b >> 4) * 128 + (lane & 7) * 16 + (b & 12), tag);
        sts1(par + PAR_CONST + 60, 0);
        if (lane < 8) sts1(par + PAR_CONST + 16 + lane * 4, (b & 2) ? ((b & 1) ? g.w : g.z) : ((b & 1) ? g.y : g.x));
        else if (lane < 10) sts2(par + PAR_CONST + (lane - 8) * 8, __float_as_uint(untag_sum(g.x, g.y) + untag_sum(g.z, g.w)), epoch);
      }
      __syncwarp();
#pragma unroll 1
      for (int q = 0; q < 32; q++) {
        st_b128(g_xch + ((size_t)b * 8 * 256 + q * 64 + t2) * 4, (epoch & 1) << 16, 0, 0, 0);
        __nanosleep(RSL);
      }
      for (int q = 0; q < 2; q++) st_relaxed4(g_stats + (((rb * 8 + q * 4 + (t2 >> 4)) * 8 + cj) * 16 + (t2 & 15)) * 4, 0, 0, 0, 0);
      if (b < NFFN)
        for (int q = 0; q < 2; q++) st_relaxed4(ypart_slot(b, q * 64 + t2), 0, 0, 0, 0);
      st_relaxed4(g_row + rb * 2 * DM + (t2 >> 5) * DM + cj * 128 + (t2 & 31) * 4, 0, 0, 0, 0);
      __threadfence();
      mbar_arrive(bar_par);
      mbar_wait(bar_gate, 0);
      uint32_t have = 0, n = 0;
      while (true) {
        const uint32_t st = lds1(par + PAR_CONST + 60) >> 7;
        if ((st & 31) != have) {
          const uint32_t* hsrc = g_row + (st & 15) * 2 * DM + t2 * 4;
          uint4 hv[4];
          bool ok = true;
#pragma unroll
          for (int i = 0; i < 4; i++) hv[i] = ld_pairs(hsrc + i * 256);
#pragma unroll
          for (int i = 0; i < 4; i++) {
            sts2(base + ((FT_G >> i * 4) & 15) * UNIT + (warp & 1) * 8192 + 256 + lane * 8, hv[i].x, hv[i].z);
            ok = ok && hv[i].y == tag && hv[i].w == tag;
          }
          have = __all_sync(0xffffffffu, ok) ? st & 31 : 0;
        }
        if ((st ^ have) == 32) break;
        watchdog(n);
      }
      mbar_arrive(bar_sel);
    }
    __syncwarp();
    cluster_arrive();
    {
      const uint32_t tag = epoch % 3 + 1, t3 = tid - 256;
      mbar_wait(bar_win, 0);
      uint2 win = lds2(par + PAR_CONST + 56);
      win.y &= 0x7ff;
      const uint32_t* fsrc = g_row + (win.y >> 7) * 2 * DM + (b >> 4) * 128 + (t3 & 7) * 16 + (b & 6) * 2 + ((b >> 2) & 2);
      const uint32_t* ysrc = ypart_slot(min(t3, NFFN - 1), b);
      uint2 fh = ld_pair(fsrc), fx = ld_pair(fsrc + DM);
      uint4 ya = ld_b128(ysrc);
      const float rwin = __uint_as_float(((int)win.x < 0 ? win.x & 0x7fffffffu : ~win.x) & ~0x1ffu);
      const float rs = rbf(rcp(1.f + __expf(-rbf(rwin))));
      uint32_t n = 0;
      while (__any_sync(0xffffffffu, fh.y != tag || fx.y != tag)) { fh = ld_pair(fsrc); fx = ld_pair(fsrc + DM); watchdog(n); }
      while (true) {
        const bool miss = ((ya.x & 1) | (ya.y & 1) << 1) != tag;
        if (!__any_sync(0xffffffffu, miss)) break;
        if (miss) ya = ld_b128(ysrc);
        watchdog(n);
      }
      PROF(8, t3 == 0, 5);
      float y[8] = {bf_lo(ya.x & ~1u), bf_hi(ya.x), bf_lo(ya.y & ~1u), bf_hi(ya.y), bf_lo(ya.z), bf_hi(ya.z), bf_lo(ya.w), bf_hi(ya.w)};
#pragma unroll
      for (int h = 4; h > 0; h >>= 1) {
        const bool up = lane & (h * 2);
#pragma unroll
        for (int e = 0; e < h; e++) y[e] = (up ? y[e + h] : y[e]) + __shfl_xor_sync(0xffffffffu, up ? y[e] : y[e + h], h * 2);
      }
      y[0] += __shfl_xor_sync(0xffffffffu, y[0], 1);
      if (!(lane & 1)) sts1(par + PAR_RED + 64 + t3 * 2, __float_as_uint(y[0]));
      bar_sync(4, 128);
      if (t3 < 8) {
        float y0 = 0.f;
#pragma unroll
        for (int w7 = 0; w7 < 7; w7++) y0 += __uint_as_float(lds1(par + PAR_RED + 64 + w7 * 32 + t3 * 4));
        const uint32_t gv = lds1(par + PAR_CONST + 16 + t3 * 4);
        const uint32_t upd = hmul2(pack_bf(y0, y0), pack_bf(rs, rs));
        const uint32_t r = hadd2(fx.x, hmul2(__byte_perm(gv, gv, 0x3232), hadd2(fh.x, upd)));
        reinterpret_cast<uint16_t*>(P.out)[(size_t)win.y * DM + (b >> 4) * 128 + t3 * 16 + (b & 15)] = (b & 1) ? r >> 16 : r;
        if (b == 0 && t3 == 0) st_relaxed(&g_epoch, epoch + 1);
      }
      PROF(31, t3 == 0, 36);
    }
    cluster_wait();
  } else {
    const int wg = warp >> 2;

    const uint32_t epoch = ld_relaxed(&g_epoch);
    asm volatile("setmaxnreg.inc.sync.aligned.u32 232;");
    uint32_t tag = 0;
    const uint32_t rempty = lane < 2 ? mapa(bempty, lane & 1) : 0;
    constexpr uint32_t GE = NSLOT * 8 + 32;
    float o[64], s[64];
#pragma unroll 1
    for (int ps = 0; ps < 3; ps++) {
      {
        const uint32_t xt = ps == 1 ? XT1 : XT2, wt = ps == 1 ? WT1 : WT2;
        const int nst = ps == 2 ? 28 : 14;
        if (ps == 0) {
          float ga[64], gb[64];
#pragma unroll
          for (int i = 0; i < 64; i++) { ga[i] = 0.f; gb[i] = 0.f; }
          uint32_t a[2][16];
          const uint32_t l = fresh_lane();
          uint32_t* const pmod = g_modp + rank * 2 * DM + (b >> 1) * 32 + l;
          uint32_t* const pln = g_ln1 + (rb * 128 + cj * 16 + warp) * 4;
          uint32_t sc[8];
#pragma unroll
          for (int k = 0; k < 8; k++) sc[k] = ldg_nc1(P.c + rank * 512 + warp * 64 + k * 8 + (l & 3) * 2);
          if (warp == 0) st_relaxed(pmod, 0);
          if (l == 0) { st_b128(pln, 0, 0, 0, 0); st_b128(pln + 32, 0, 0, 0, 0); }
          bar_sync(1, 320);
          tag = epoch % 3 + 1;
          auto row_stats = [&](int part) {
            const uint32_t xa = base + (2 + part) * GST_BYTES + warp * 2048 + l * 16;
            mbar_wait(bar_hx + part * 8, 0);
            float ds[4] = {0.f, 0.f, 0.f, 0.f}, q0[4] = {0.f, 0.f, 0.f, 0.f}, q1[4] = {0.f, 0.f, 0.f, 0.f};
#pragma unroll
            for (int q = 0; q < 4; q++) {
              const uint4 xv = lds4(xa + q * 512);
              mma16816(ds, xv.x, xv.z, xv.y, xv.w, 0x3f803f80u, 0x3f803f80u);
              mma16816(q0, xv.x, xv.z, xv.y, xv.w, xv.x, xv.y);
              mma16816(q1, xv.x, xv.z, xv.y, xv.w, xv.z, xv.w);
            }
            float su = ds[0] + ds[2], sq = (l & 4) ? q0[1] + q1[3] : q0[0] + q1[2];
            sq = __shfl_sync(0xffffffffu, sq, (l & 28) + (l >> 3));
#pragma unroll
            for (int o = 16; o > 2; o >>= 1) { su += __shfl_xor_sync(0xffffffffu, su, o); sq += __shfl_xor_sync(0xffffffffu, sq, o); }
            const float mean = su * (1.f / DM);
            float mb, sd;
            ln_scalars(mean, fmaxf(sq * (1.f / DM) - mean * mean, 0.f), mb, sd);
            uint32_t ih, il;
            split_inv(sd, ih, il);
            if (l == 0) st_b128(pln + part * 32, pack_bf(mb, mb), ih, il, tag);
          };
          auto gemv = [&]() {
            const uint32_t fr = (l & 7) + (l >> 4) * 8, tq = l & 3;
            const uint32_t wa = stage + warp * 4096 + fr * 64 + ((((l >> 3) & 1) ^ ((fr >> 1) & 3)) << 4);
            float d0[4] = {0.f, 0.f, 0.f, 0.f}, d1[4] = {0.f, 0.f, 0.f, 0.f};
#pragma unroll
            for (int ks = 0; ks < 4; ks++) {
              uint32_t w[8];
              ldmatrix4t(wa + ks * 1024, w[0], w[1], w[2], w[3]);
              ldmatrix4t((wa ^ 32) + ks * 1024, w[4], w[5], w[6], w[7]);
              mma16816(d0, w[0], w[1], w[2], w[3], sc[2 * ks], sc[2 * ks + 1]);
              mma16816(d1, w[4], w[5], w[6], w[7], sc[2 * ks], sc[2 * ks + 1]);
            }
            sts1(base + 2 * GST_BYTES + warp * 2048 + (tq * 8 + (l >> 2)) * 4, __float_as_uint((tq & 2) ? ((tq & 1) ? d1[2] : d1[0]) : ((tq & 1) ? d0[2] : d0[0])));
            bar_sync(1, 256);
            if (warp == 0) {
              float s = 0.f;
#pragma unroll
              for (int w8 = 0; w8 < 8; w8++) s += __uint_as_float(lds1(base + 2 * GST_BYTES + w8 * 2048 + l * 4));
              st_relaxed(pmod, (__float_as_uint(s) & ~3u) | tag);
            }
            PROF(1, tid == 0, 3);
          };
          row_stats(0);
#pragma unroll
          for (int k = 0; k < 8; k++) sc[k] = pack_bf(silu_f(bf_lo(sc[k])), silu_f(bf_hi(sc[k])));
          keep(sc);
          if (!late) { mbar_wait(bar_hw, 0); gemv(); }
          row_stats(1);
          PROF(1, tid == 0, 4);
          cluster_wait();
          if (wg == 1) bar_arrive(2, 256);
          uint32_t fa[4];
#pragma unroll
          for (int kk = 0; kk < 4; kk++) fa[kk] = (base + wg * 8192 + frag_offset(warp)) ^ (kk * 32);
          const uint32_t mt = par + (l & 3) * 16;
          auto fetch = [&](int i, uint32_t (&f)[16], uint32_t z) {
            mbar_wait(xfull + (i & 3) * 8, i >> 2);
#pragma unroll
            for (int kk = 0; kk < 4; kk++) ldmatrix4(fa[kk] + (i & 3) * GST_BYTES + z, f[4 * kk], f[4 * kk + 1], f[4 * kk + 2], f[4 * kk + 3]);
          };
          const bool oddw = warp & 2;
          uint4 r0, r1;
          {
            const uint32_t t7 = (warp & 1) * 64 + (l >> 4) * 32 + (l & 15);
            const uint32_t* pm = g_modp + wg * DM + ((cj * 128 + t7 * 4) & (DM - 1));
            const uint32_t* pr = g_ln1 + (rb * 128 + warp * 16 + (l >> 2)) * 4;
            uint4 m0 = make_uint4(tag, tag, tag, tag), m1 = m0;
            mbar_wait(bar_hw, 0);
            if (!GL && late) gemv();
            if (!oddw) { m0 = ld_relaxed4(pm); m1 = ld_relaxed4(pm + 2 * DM); }
            r0 = ld_b128(pr); r1 = ld_b128(pr + 32);
            if (GL && late) gemv();
            fetch(0, a[0], 0); fetch(1, a[1], 0);
            uint32_t n = 0;
            bool written = false;
#pragma unroll 1
            while (true) {
              uint32_t miss;
              asm volatile("{ .reg .pred p0, p1, p2, p3; .reg .b32 t, u;\n"
                           "lop3.b32 t, %1, %2, %19, 0x7e; lop3.b32 u, %3, %4, %19, 0x7e; or.b32 t, t, u; and.b32 t, t, 3; setp.ne.u32 p0, t, 0;\n"
                           "lop3.b32 t, %5, %6, %19, 0x7e; lop3.b32 u, %7, %8, %19, 0x7e; or.b32 t, t, u; and.b32 t, t, 3; setp.ne.u32 p1, t, 0;\n"
                           "setp.ne.u32 p2, %12, %19; setp.ne.u32 p3, %16, %19;\n"
                           "@p0 ld.relaxed.gpu.global.v4.u32 {%1, %2, %3, %4}, [%17];\n"
                           "@p1 ld.relaxed.gpu.global.v4.u32 {%5, %6, %7, %8}, [%17 + 8192];\n"
                           "@p2 ld.relaxed.gpu.global.v4.u32 {%9, %10, %11, %12}, [%18];\n"
                           "@p3 ld.relaxed.gpu.global.v4.u32 {%13, %14, %15, %16}, [%18 + 128];\n"
                           "or.pred p0, p0, p1; or.pred p2, p2, p3; vote.sync.any.pred p0, p0, 0xffffffff; vote.sync.any.pred p2, p2, 0xffffffff;\n"
                           "selp.u32 t, 1, 0, p0; selp.u32 u, 2, 0, p2; or.b32 %0, t, u; }"
                           : "=r"(miss), "+r"(m0.x), "+r"(m0.y), "+r"(m0.z), "+r"(m0.w), "+r"(m1.x), "+r"(m1.y), "+r"(m1.z), "+r"(m1.w),
                             "+r"(r0.x), "+r"(r0.y), "+r"(r0.z), "+r"(r0.w), "+r"(r1.x), "+r"(r1.y), "+r"(r1.z), "+r"(r1.w)
                           : "l"(pm), "l"(pr), "r"(tag) : "memory");
              if (!(miss & 1) && !written) {
                written = true;
                if (!oddw) write_table(par, wg, t7, m0, m1);
                mbar_arrive(bar_mod);
              }
              if (!miss) break;
              watchdog(n);
            }
          }
          const uint32_t zero = r0.w ^ tag;
          auto normalize = [&](uint32_t (&f)[16]) {
#pragma unroll
            for (int k = 0; k < 16; k += 2) { f[k] = ln_norm(f[k], r0.x, r0.y, r0.z); f[k + 1] = ln_norm(f[k + 1], r1.x, r1.y, r1.z); }
          };
          auto modulate = [&](int i, uint32_t (&f)[16]) {
#pragma unroll
            for (int kk = 0; kk < 4; kk++) {
              const uint4 m = lds4(mt + slice_of(i) * 256 + kk * 64);
              f[4 * kk] = hfma2(f[4 * kk], m.x, m.z); f[4 * kk + 1] = hfma2(f[4 * kk + 1], m.x, m.z);
              f[4 * kk + 2] = hfma2(f[4 * kk + 2], m.y, m.w); f[4 * kk + 3] = hfma2(f[4 * kk + 3], m.y, m.w);
            }
            keep(f);
            mbar_arrive_pred(xempty + (i & 3) * 8, l == 0);
          };
          auto publish = [&](int u, uint32_t (&f)[16]) {
#pragma unroll
            for (int kk = 0; kk < 4; kk++) stmatrix4(fa[kk] + OFF_STAGE + u * UNIT, f[4 * kk], f[4 * kk + 1], f[4 * kk + 2], f[4 * kk + 3]);
            __syncwarp();
            mbar_arrive_pred(bar_hpub + u * 8, l == 0);
          };
          auto multiply = [&](int i, uint32_t (&f)[16]) {
            mbar_wait(gfull + (i & 3) * 8, i >> 2);
            const uint64_t db = make_desc(base + (i & 3) * GST_BYTES + UNIT, 8192, 1024);
            wg_fence();
#pragma unroll
            for (int kk = 0; kk < 4; kk++) mma256_rs(ga, gb, f[4 * kk], f[4 * kk + 1], f[4 * kk + 2], f[4 * kk + 3], db + kk * 128);
            wg_commit();
          };
          auto next = [&](int i, uint32_t (&f)[16]) {
            wg_wait<1>();
            mbar_arrive_cl(rempty, GE + ((i + 2) & 3) * 8);
            uint32_t z = zero;
#pragma unroll
            for (int k = 0; k < 16; k += 2) asm volatile("lop3.b32 %0, %1, %2, %0, 0xA8;" : "+r"(z) : "r"(f[k]), "r"(f[k + 1]));
            fetch(i, f, z);
            normalize(f);
            if (i == 2) { keep(f); mbar_wait(bar_mod2, 0); }
            modulate(i, f); multiply(i, f);
          };
          normalize(a[0]);
          if (!N1L) normalize(a[1]);
          keep(a[0]); keep(a[1]);
          mbar_wait(bar_mod, 0);
          PROF(1, tid == 0, 2);
          modulate(0, a[0]); multiply(0, a[0]); publish(0, a[0]);
          if (N1L) { keep(a[1]); normalize(a[1]); }
          modulate(1, a[1]); multiply(1, a[1]);
#pragma unroll 1
          for (int i = 2; i < NRS; i += 2) {
            next(i, a[0]);
            if (i == 2) publish(1, a[0]);
            next(i + 1, a[1]);
          }
          wg_wait<1>();
          mbar_arrive_cl(rempty, GE + ((NRS + 2) & 3) * 8);
#pragma unroll 1
          for (int i = NRS; i < 14; i++) {
            mbar_wait(xfull + (i & 3) * 8, (i >> 2) & 1);
            mbar_wait(gfull + (i & 3) * 8, (i >> 2) & 1);
            const uint32_t xa = base + (i & 3) * GST_BYTES;
            const uint64_t da = make_desc(xa + wg * 8192, 16, 1024), db = make_desc(xa + UNIT, 8192, 1024);
            if (i == 13) bar_sync(2 + wg, 256);
            wg_fence();
#pragma unroll
            for (int kk = 0; kk < 4; kk++) mma256_ss(ga, gb, da + kk * 2, db + kk * 128, 1);
            wg_commit();
            if (i == 13) bar_arrive(3 - wg, 256);
            wg_wait<1>();
            uint32_t z = zero;
#pragma unroll
            for (int k = 0; k < 16; k += 2) asm volatile("lop3.b32 %0, %1, %2, %0, 0xA8;" : "+r"(z) : "r"(a[1][k]), "r"(a[1][k + 1]));
            mbar_arrive_cl(rempty, GE + ((i + 3) & 3) * 8 + z);
            mbar_arrive_pred(xempty + ((i + 3) & 3) * 8, l == 0 && i != NRS);
          }
          mbar_wait(xfull + 16, 1);
          wg_wait<0>();
          keep(ga); keep(gb);
#pragma unroll
          for (int i = 0; i < 64; i++) {
            asm volatile("mov.b32 %0, %1;" : "=f"(s[i]) : "f"(ga[i]));
            asm volatile("mov.b32 %0, %1;" : "=f"(o[i]) : "f"(gb[i]));
          }
        } else {
          float ga[64], gb[64];
#pragma unroll
          for (int i = 0; i < 64; i++) {
            asm volatile("mov.b32 %0, %1;" : "=f"(ga[i]) : "f"(s[i]));
            asm volatile("mov.b32 %0, %1;" : "=f"(gb[i]) : "f"(o[i]));
          }
#pragma unroll 1
          for (int i = 0; i < nst; i++) {
            mbar_wait(gfull + (i & 3) * 8, (i >> 2) & 1);
            const uint64_t da = make_desc(base + unit_of(xt, i & 3) + wg * 8192, 16, 1024), db = make_desc(base + unit_of(wt, i & 3), 8192, 1024);
            if (i == nst - 1) bar_sync(2 + wg, 256);
            wg_fence();
#pragma unroll
            for (int kk = 0; kk < 4; kk++) mma256_ss(ga, gb, da + kk * 2, db + kk * 128, kk ? 1 : i);
            wg_commit();
            if (i == nst - 1) bar_arrive(3 - wg, 256);
            wg_wait<1>();
            mbar_arrive_cl(rempty, GE + ((i + 3) & 3) * 8, i != 0);
            PROF(4, tid == 0 && (i & 3) == 0, 40 + (ps - 1) * 4 + i / 4);
          }
          wg_wait<0>();
          keep(ga); keep(gb);
#pragma unroll
          for (int i = 0; i < 64; i++) {
            asm volatile("mov.b32 %0, %1;" : "=f"(s[i]) : "f"(ga[i]));
            asm volatile("mov.b32 %0, %1;" : "=f"(o[i]) : "f"(gb[i]));
          }
        }
        mbar_arrive_cl(rempty, GE + (ps == 2 ? 24 : 8));
        if (ps == 2) break;
      }
      const uint32_t qw = base + wg * 8192, qt = QT >> (16 * ps), at = ps ? AT1 : AT0;
      {
        const uint32_t wt = ps ? WT1 : WT0;
        const uint64_t da0 = make_desc(qw + unit_of(qt, 2), 16, 1024), da1 = make_desc(qw + unit_of(qt, 3), 16, 1024);
        const uint64_t db0 = make_desc(base + unit_of(wt, 2), 8192, 1024), db1 = make_desc(base + unit_of(wt, 3), 8192, 1024);
        mbar_wait(gfull + 16, 1);
        bar_sync(2 + wg, 256);
        wg_fence();
#pragma unroll
        for (int kk = 0; kk < 4; kk++) mma_ss<1>(s, da0 + kk * 2, db0 + kk * 128, 1);
        wg_commit();
        mbar_wait(xfull + 24, 1);
        mbar_wait(gfull + 24, 1);
        wg_fence();
#pragma unroll
        for (int kk = 0; kk < 4; kk++) mma_ss<1>(s, da1 + kk * 2, db1 + kk * 128, 1);
        wg_commit();
        bar_arrive(3 - wg, 256);
        mbar_wait(ps == 0 ? bar_pread : bar_ofree + 8, 0);
        wg_wait<0>();
        keep(s);
        PROF(2, tid == 0, 8 + ps * 8);
        uint32_t q[32];
        pack_p(s, q);
#pragma unroll
        for (int i = 0; i < 4; i++) stmatrix4((qw + unit_of(qt, 0) + frag_offset(warp)) ^ (i << 5), q[4 * i], q[4 * i + 1], q[4 * i + 2], q[4 * i + 3]);
        keep(q);
        bar_sync(2 + wg, 256);
        wg_fence();
#pragma unroll
        for (int kk = 0; kk < 8; kk++) mma_ss<1>(o, (kk < 4 ? da0 : da1) + (kk & 3) * 2, (kk < 4 ? db0 : db1) + UNIT / 16 + (kk & 3) * 128, 1);
        wg_commit();
        mbar_wait(bfull, 0);
        wg_fence();
        const uint64_t dk = make_desc(base + unit_of(at, 0), 16, 1024);
#pragma unroll
        for (int kk = 0; kk < 8; kk++) mma_rs<0>(s, q[4 * kk], q[4 * kk + 1], q[4 * kk + 2], q[4 * kk + 3], dk + (kk >> 2) * 1024 + (kk & 3) * 2, kk != 0);
        wg_commit();
        bar_arrive(3 - wg, 256);
#pragma unroll
        for (int i = 4; i < 8; i++) stmatrix4((qw + unit_of(qt, 1) + frag_offset(warp)) ^ ((i & 3) << 5), q[4 * i], q[4 * i + 1], q[4 * i + 2], q[4 * i + 3]);
        wg_wait<1>();
        keep(o);
        mbar_arrive_cl(rempty, GE + 16);
        mbar_arrive_cl(rempty, GE + 24);
        store_chunk<0>(o, qw + unit_of(qt, 2) + frag_offset(warp));
        store_chunk<1>(o, qw + unit_of(qt, 3) + frag_offset(warp));
        wg_wait<0>();
        keep(s);
        mbar_arrive_cl(rempty, 0);
      }
      PROF(4, tid == 0 && ps == 1, 61);
      float l0 = 0.f, l1 = 0.f, f0 = 0.f, f1 = 0.f;
      auto step = [&](auto odd_c, const int j, uint32_t (&pw)[32], uint32_t (&pr)[32]) {
        constexpr bool ODD = decltype(odd_c)::value;
        const bool first = !ODD && (j & 2) == 0, last = ODD && j == 7;
        const uint32_t ph = (j >> 1) & 1;
        float i0, i1, a0, a1;
        const bool so = !ODD && j == 4;
        if (so) { i0 = inv_quad_sum(l0); i1 = inv_quad_sum(l1); l0 = 0.f; l1 = 0.f; }
        if (first) {
          int m0 = max(__float_as_int(s[0]), __float_as_int(s[1])), m1 = max(__float_as_int(s[2]), __float_as_int(s[3]));
#pragma unroll
          for (int i = 1; i < 16; i++) {
            m0 = __vimax3_s32(m0, __float_as_int(s[4 * i]), __float_as_int(s[4 * i + 1]));
            m1 = __vimax3_s32(m1, __float_as_int(s[4 * i + 2]), __float_as_int(s[4 * i + 3]));
          }
          m0 = max(m0, __shfl_xor_sync(0xffffffffu, m0, 1)); m1 = max(m1, __shfl_xor_sync(0xffffffffu, m1, 1));
          m0 = max(m0, __shfl_xor_sync(0xffffffffu, m0, 2)); m1 = max(m1, __shfl_xor_sync(0xffffffffu, m1, 2));
          f0 = fmaf(__int_as_float(m0), SCL2, BIAS); f1 = fmaf(__int_as_float(m1), SCL2, BIAS);
        }
        bool redo = false;
        while (true) {
          if (redo) {
            float m0 = fmaxf(s[0], s[1]), m1 = fmaxf(s[2], s[3]);
#pragma unroll
            for (int i = 1; i < 16; i++) { m0 = fmaxf(m0, fmaxf(s[4 * i], s[4 * i + 1])); m1 = fmaxf(m1, fmaxf(s[4 * i + 2], s[4 * i + 3])); }
            m0 = fmaxf(m0, __shfl_xor_sync(0xffffffffu, m0, 1)); m1 = fmaxf(m1, __shfl_xor_sync(0xffffffffu, m1, 1));
            m0 = fmaxf(m0, __shfl_xor_sync(0xffffffffu, m0, 2)); m1 = fmaxf(m1, __shfl_xor_sync(0xffffffffu, m1, 2));
            m0 = fmaf(m0, SCL2, BIAS); m1 = fmaf(m1, SCL2, BIAS);
            if (!first) {
              m0 = fmaxf(m0, f0); m1 = fmaxf(m1, f1);
              const float c0 = ex2(f0 - m0), c1 = ex2(f1 - m1);
              l0 *= c0; l1 *= c1;
              wg_wait<0>();
              keep(o);
#pragma unroll
              for (int i = 0; i < 16; i++) { o[4 * i] *= c0; o[4 * i + 1] *= c0; o[4 * i + 2] *= c1; o[4 * i + 3] *= c1; }
            }
            f0 = m0; f1 = m1;
          }
          float b0 = 0.f, b1 = 0.f;
          a0 = 0.f; a1 = 0.f;
#pragma unroll
          for (int i = 0; i < 16; i++) {
            const float e0 = ex2(fmaf(s[4 * i], SCL2, -f0)), e1 = ex2(fmaf(s[4 * i + 1], SCL2, -f0));
            const float e2 = ex2(fmaf(s[4 * i + 2], SCL2, -f1)), e3 = ex2(fmaf(s[4 * i + 3], SCL2, -f1));
            a0 += e0; b0 += e1; a1 += e2; b1 += e3;
            pw[2 * i] = pack_bf(e0, e1); pw[2 * i + 1] = pack_bf(e2, e3);
            if (i == VREL) {
#pragma unroll
              for (int k = 0; k < 2 * VREL + 2; k++) asm volatile("" : "+r"(pw[k])::"memory");
              mbar_wait(bar_mod, 0);
              wg_wait<0>();
              mbar_arrive_cl(rempty, ODD ? 16 : 0, !redo && (ODD || j));
#pragma unroll
              for (int k = 4 * VREL + 4; k < 64; k++) asm volatile("" : "+f"(s[k])::"memory");
            }
          }
          a0 += b0; a1 += b1;
          if (redo) break;
          redo = __any_sync(0xffffffffu, !(a0 + a1 < 1.f));
          if (!redo) break;
        }
        l0 += a0; l1 += a1;
        keep(pw);
        keep(o);
        if (so) store_chunk<0>(o, i0, i1, qw + unit_of(qt, 0) + frag_offset(warp));
        keep(o);
        if (j == (ODD ? 5 : 0)) { fence_async_smem(); if (ODD) mbar_arrive(bar_ofull + wg * 8); }
        mbar_wait(bfull + (ODD ? 24 : 8), ph);
        bar_sync(2 + wg, 256);
        if (!last) {
          const uint32_t qn = qt >> (j >= 3 ? 8 : 0);
          wg_fence();
          issue_qk(s, qw + unit_of(qn, 0), qw + unit_of(qn, 1), base + unit_of(at, ODD ? 3 : 1));
          wg_commit();
          mbar_wait(bfull + (ODD ? 0 : 16), ODD ? ph ^ 1 : ph);
        }
        if (so) { store_chunk<1>(o, i0, i1, qw + unit_of(qt, 1) + frag_offset(warp)); keep(o); }
        wg_fence();
        issue_pv(o, pw, base + unit_of(at, ODD ? (last ? 3 : 0) : 2), !first);
        wg_commit();
        bar_arrive(3 - wg, 256);
        wg_wait<1>();
        keep(s);
        mbar_arrive_cl(rempty, ODD ? 24 : 8, !last);
        PROF(4, tid == 0 && ps == 1, 51 + j);
      };
      uint32_t pa[32], pb[32];
#pragma unroll 1
      for (int j = 0; j < 8; j += 2) {
        step(std::false_type{}, j, pa, pb);
        step(std::true_type{}, j + 1, pb, pa);
      }
      {
        const float i0 = inv_quad_sum(l0), i1 = inv_quad_sum(l1);
        wg_wait<0>();
        keep(o);
        mbar_arrive_cl(rempty, 24);
        store_chunk<0>(o, i0, i1, qw + unit_of(qt, 2) + frag_offset(warp));
        store_chunk<1>(o, i0, i1, qw + unit_of(qt, 3) + frag_offset(warp));
        fence_async_smem();
        mbar_arrive(bar_ofull + 16 + wg * 8);
      }
      PROF(2, tid == 0, 10 + ps * 8);
    }

    const int ln = fresh_lane(), g = ln >> 2, tq = ln & 3, ct = warp * 32 + ln;
    const bool lane0 = ln == 0;
    const int lrow0 = warp * 16 + g;
    const uint32_t res = base + OFF_RES, trow = res + wg * 8192 + frag_offset(warp);
    uint32_t xr[32];
    uint4 sv[4], own;
    uint32_t* const sg = g_stats + (rb * 8 + warp) * 512 + g * 4;
    uint32_t* sp[4];
#pragma unroll
    for (int k = 0; k < 4; k++) sp[k] = sg + (tq & 1) * 32 + (((tq >> 1) ^ (cj >> 2)) * 4 + (k ^ (cj & 3))) * 64;
    {
      const uint64_t da = make_desc(base + wg * 8192, 16, 1024), db = make_desc(base, 8192, 1024);
      constexpr int U = UNIT / 16;
#define HALF_STAGE(acc, xu, wu) _Pragma("unroll") for (int kk = 0; kk < 4; kk++) mma_ss<1>(acc, da + (xu) * U + kk * 2, db + (wu) * U + kk * 128, 1)
      PROF(10, ct == PT, 19); STAMP(0);
      cluster_arrive();
      mbar_wait(gfull, 1);
      mbar_wait(gfull + 8, 1);
      bar_sync(2 + wg, 256);
      wg_fence();
      HALF_STAGE(o, 7, 1);
      HALF_STAGE(o, 8, 3);
      wg_commit();
      STAMP(16);
      mbar_wait(gfull + 16, 1);
      STAMP(17);
      wg_fence();
      HALF_STAGE(o, 6, 11);
      wg_commit();
      bar_arrive(3 - wg, 256);
      mbar_wait(bar_par, 0);
      uint32_t* xo = g_xch + ((size_t)b * 8 * 256 + ct) * 4;
      const uint32_t* xi = g_xch + ((size_t)(b ^ 2) * 8 * 256 + ct) * 4;
      const uint32_t par1 = (~lds1(par + PAR_CONST + 4) & 1) << 16;
      wg_wait<1>();
      mbar_arrive_pred(bar_rel, lane0);
      wg_wait<0>();
      keep(o);
      mbar_arrive_pred(bar_ring, lane0);
      PROF(8, ct == PT, 20); STAMP(1);
#define SEND(i) st_b128(xo + (i) * 1024, (pack_bf(o[8 * (i)], o[8 * (i) + 1]) & ~0x10000u) | par1, pack_bf(o[8 * (i) + 2], o[8 * (i) + 3]), \
                        pack_bf(o[8 * (i) + 4], o[8 * (i) + 5]), pack_bf(o[8 * (i) + 6], o[8 * (i) + 7]))
#pragma unroll
      for (int i = 0; i < NS1; i++) SEND(i);
      PROF(8, ct == PT, 21); STAMP(2);
      bar_sync(2 + wg, 256);
      wg_fence();
      HALF_STAGE(s, 7, 0);
      HALF_STAGE(s, 8, 2);
      HALF_STAGE(s, 6, 10);
      wg_commit();
      bar_arrive(3 - wg, 256);
      STAMP(18);
      mbar_wait(gfull + 24, 1);
#pragma unroll
      for (int i = NS1; i < 8; i++) SEND(i);
      uint4 v[8];
      STAMP(19);
      mbar_wait(bar_xres, 0);
      wg_wait<0>();
      mbar_arrive_pred(bar_ring + 8, lane0);
      bar_sync(2 + wg, 256);
      STAMP(20);
#pragma unroll
      for (int i = 0; i < LD2; i++) v[i] = ld_b128(xi + i * 1024);
      mbar_wait(bar_xres, 0);
      wg_fence();
      HALF_STAGE(s, 9, 4);
      wg_commit();
      mbar_wait(bar_rx, 0);
      wg_fence();
      HALF_STAGE(s, 1, 5);
      wg_commit();
      bar_arrive(3 - wg, 256);
      STAMP(21);
#pragma unroll
      for (int i = LD2; i < 8; i++) v[i] = ld_b128(xi + i * 1024);
      mbar_wait(bar_xres, 0);
      wg_wait<0>();
      keep(s);
      mbar_arrive_pred(bar_ring + 16, lane0);
      PROF(10, ct == PT, 23); STAMP(4);
#pragma unroll
      for (int i = 0; i < 16; i += 2) ldmatrix4((trow ^ ((i & 7) << 4)) + (i >> 3) * 16384, xr[2 * i], xr[2 * i + 1], xr[2 * i + 2], xr[2 * i + 3]);
      uint32_t ga[16];
      uint4 bw[8];
#pragma unroll
      for (int i = 0; i < 8; i++) {
        if (!(i & 1)) {
          const uint4 t = lds4(par + PAR_SINK + i * 32 + tq * 16);
          ga[2 * i] = t.x; ga[2 * i + 1] = t.y; ga[2 * i + 2] = t.z; ga[2 * i + 3] = t.w;
        }
        bw[i] = lds4(par + PAR_T1 + i * 64 + tq * 16);
        if (!(g & 1)) { bw[i].x = 0x3f803f80u; bw[i].y = 0x3f803f80u; }
      }
      uint32_t pk[32];
      pack_p(s, pk);
      const uint32_t par2 = (~lds1(par + PAR_CONST + 12) & 1) << 16;
      {
        uint32_t n = 0, miss;
        do {
          miss = 0;
#pragma unroll
          for (int i = 0; i < 8; i++) miss |= v[i].x ^ par2;
          miss = __any_sync(0xffffffffu, miss & 0x10000u);
          if (miss) {
#pragma unroll
            for (int i = 0; i < 8; i++)
              asm volatile("{ .reg .pred p; .reg .b32 t; xor.b32 t, %0, %5; and.b32 t, t, 0x10000; setp.ne.u32 p, t, 0;\n"
                           "@p ld.relaxed.gpu.global.v4.u32 {%0, %1, %2, %3}, [%4]; }"
                           : "+r"(v[i].x), "+r"(v[i].y), "+r"(v[i].z), "+r"(v[i].w) : "l"(xi + i * 1024), "r"(par1) : "memory");
          }
          watchdog(n);
        } while (miss);
      }
      PROF(8, ct == PT, 22); STAMP(3);
      float ds[4] = {0.f, 0.f, 0.f, 0.f}, dl[4] = {0.f, 0.f, 0.f, 0.f}, q0[4] = {0.f, 0.f, 0.f, 0.f}, q1[4] = {0.f, 0.f, 0.f, 0.f};
#pragma unroll
      for (int i = 0; i < 8; i++) {
        const uint32_t u0 = hfma2(ga[2 * i], hadd2(pk[4 * i], v[i].x & ~0x10000u), xr[4 * i]);
        const uint32_t u1 = hfma2(ga[2 * i], hadd2(pk[4 * i + 1], v[i].y), xr[4 * i + 1]);
        const uint32_t u2 = hfma2(ga[2 * i + 1], hadd2(pk[4 * i + 2], v[i].z), xr[4 * i + 2]);
        const uint32_t u3 = hfma2(ga[2 * i + 1], hadd2(pk[4 * i + 3], v[i].w), xr[4 * i + 3]);
        xr[4 * i] = u0; xr[4 * i + 1] = u1; xr[4 * i + 2] = u2; xr[4 * i + 3] = u3;
        mma16816(ds, u0, u1, u2, u3, bw[i].x, bw[i].y);
        mma16816(dl, u0, u1, u2, u3, bw[i].z, bw[i].w);
        mma16816(q0, u0, u1, u2, u3, u0, u2);
        mma16816(q1, u0, u1, u2, u3, u1, u3);
      }
      const float sqa = (g & 1) ? q0[1] : q0[0], sqb = (g & 1) ? q1[3] : q1[2], dta = ds[1] + dl[1], dtb = ds[3] + dl[3];
      if (tq == (g >> 1)) {
        st_b128(sg + cj * 64, __float_as_uint(ds[0]), __float_as_uint(sqa), __float_as_uint(dta), tag);
        st_b128(sg + cj * 64 + 32, __float_as_uint(ds[2]), __float_as_uint(sqb), __float_as_uint(dtb), tag);
      }
#pragma unroll
      for (int k = 0; k < 4; k++) sv[k] = ld_b128(sp[k]);
      mbar_wait(bar_xres, 0);
      const float sqc = __shfl_sync(0xffffffffu, sqa, g * 4 + (g >> 1)), sqd = __shfl_sync(0xffffffffu, sqb, g * 4 + (g >> 1));
      own = (tq & 1) ? make_uint4(__float_as_uint(ds[2]), __float_as_uint(sqd), __float_as_uint(dtb), tag)
                     : make_uint4(__float_as_uint(ds[0]), __float_as_uint(sqc), __float_as_uint(dta), tag);
    }
    PROF(8, ct == PT, 29); STAMP(5);
    uint32_t mm, ih, il;
    float rbest;
    uint32_t wf[128];
    const uint32_t frow = (ln & 7) + (ln >> 4) * 8;
    const uint32_t wfo = base + (warp & 1) * 8192 + frow * 64 + ((((ln >> 3) & 1) ^ ((frow >> 1) & 3)) << 4);
#define LOAD_WF(m) _Pragma("unroll") for (int f = 0; f < 16; f++) {                                                   \
      const int r = ((f >> 1) * 4 + (m) * 2 + (f & 1)) * 4;                                                           \
      ldmatrix4t(((wfo + unit_of((m) ? FT_U : FT_G, warp >> 1)) ^ ((f & 1) * 32)) + (f >> 1) * 1024, wf[r], wf[r + 1], wf[r + 2], wf[r + 3]); \
    }
    bool early;
    {
#pragma unroll
      for (int i = 0; i < 16; i += 2) stmatrix4((trow ^ ((i & 7) << 4)) + (i >> 3) * 16384, xr[2 * i], xr[2 * i + 1], xr[2 * i + 2], xr[2 * i + 3]);
      const uint4 cst = lds4(par + PAR_CONST);
      const float A1 = __uint_as_float(cst.x), A2 = __uint_as_float(cst.z);
      uint32_t n = 0;
      early = false;
#pragma unroll 1
      while (true) {
        if (!early && (b >= NFFN || __all_sync(0xffffffffu, mbar_test(bar_box + (warp >> 1) * 8, 0)))) {
          early = true;
          LOAD_WF(0);
          __syncwarp();
          mbar_arrive_pred(bar_gate, lane0);
        }
        uint32_t miss;
        asm volatile("{ .reg .pred p0, p1, p2, p3; .reg .b64 u, v; .reg .b128 w;\n"
                     "setp.ge.u32 p0, %22, 2; setp.ne.and.u32 p0, %4, %21, p0; setp.ne.u32 p1, %8, %21; setp.ne.u32 p2, %12, %21; setp.ne.u32 p3, %16, %21;\n"
                     "@p0 ld.relaxed.gpu.global.v4.u32 {%1, %2, %3, %4}, [%17];\n"
                     "@p1 ld.relaxed.gpu.global.v4.u32 {%5, %6, %7, %8}, [%18];\n"
                     "@p2 ld.relaxed.gpu.global.v4.u32 {%9, %10, %11, %12}, [%19];\n"
                     "@p3 ld.relaxed.gpu.global.v4.u32 {%13, %14, %15, %16}, [%20];\n"
                     "or.pred p0, p0, p1; or.pred p2, p2, p3; or.pred p0, p0, p2; vote.sync.any.pred p0, p0, 0xffffffff; selp.u32 %0, 1, 0, p0; }"
                     : "=r"(miss), "+r"(sv[0].x), "+r"(sv[0].y), "+r"(sv[0].z), "+r"(sv[0].w), "+r"(sv[1].x), "+r"(sv[1].y), "+r"(sv[1].z), "+r"(sv[1].w),
                       "+r"(sv[2].x), "+r"(sv[2].y), "+r"(sv[2].z), "+r"(sv[2].w), "+r"(sv[3].x), "+r"(sv[3].y), "+r"(sv[3].z), "+r"(sv[3].w)
                     : "l"(sp[0]), "l"(sp[1]), "l"(sp[2]), "l"(sp[3]), "r"(tag), "r"(tq) : "memory");
        if (!miss) break;
        watchdog(n);
      }
      const uint4 v0 = tq < 2 ? own : sv[0], v1 = sv[1], v2 = sv[2], v3 = sv[3];
      PROF(8, ct == PT, 30); STAMP(6);
      float su = (__uint_as_float(v0.x) + __uint_as_float(v1.x)) + (__uint_as_float(v2.x) + __uint_as_float(v3.x));
      float sq = (__uint_as_float(v0.y) + __uint_as_float(v1.y)) + (__uint_as_float(v2.y) + __uint_as_float(v3.y));
      float dt = (__uint_as_float(v0.z) + __uint_as_float(v1.z)) + (__uint_as_float(v2.z) + __uint_as_float(v3.z));
      su += __shfl_xor_sync(0xffffffffu, su, 2); sq += __shfl_xor_sync(0xffffffffu, sq, 2); dt += __shfl_xor_sync(0xffffffffu, dt, 2);
      const float m = su * (1.f / DM);
      float mb, sd;
      ln_scalars(m, fmaxf(sq * (1.f / DM) - m * m, 0.f), mb, sd);
      const float inv = rcp(sd);
      rbest = (dt - mb * A1) * inv + A2;
      mm = pack_bf(mb, mb);
      ih = pack_bf(inv, inv);
      const float lo = inv - bf_lo(ih);
      il = pack_bf(lo, lo);
    }
    int ibest;
    {
      const uint32_t bits = __float_as_uint(rbest);
      const uint32_t key = (((int)bits < 0 ? ~bits : bits | 0x80000000u) & ~0x1ffu) | ((127 - lrow0 - (tq & 1) * 8) << 2) | tag;
      sts1(par + PAR_RED + warp * 4, __reduce_max_sync(0xffffffffu, key));
      PROF(8, ct == PT, 38); STAMP(7);
      bar_sync(1, 256);
      const uint4 ka = lds4(par + PAR_RED), kb = lds4(par + PAR_RED + 16);
      const uint32_t k2 = max(max(max(ka.x, ka.y), max(ka.z, ka.w)), max(max(kb.x, kb.y), max(kb.z, kb.w)));
      if (ct < CR && cj == 0) st_relaxed(g_cand + ct * 512 + rb * CS, k2);
      ibest = 127 - ((k2 >> 2) & 127);
    }
    PROF(8, ct == PT, 39); STAMP(8);
    if ((ibest >> 4) == warp) {
      const int src = (ibest & 7) * 4 + ((ibest >> 3) & 1), ch = g * 2;
      const uint32_t cm = __shfl_sync(0xffffffffu, mm, src), ch_ = __shfl_sync(0xffffffffu, ih, src), cl = __shfl_sync(0xffffffffu, il, src);
      const uint32_t xa = res + (ch >> 3) * 16384 + ibest * 128 + (((ch & 7) ^ (ibest & 7)) << 4) + tq * 4;
      const uint32_t x0 = lds1(xa), x1 = lds1(xa ^ 16);
      const uint2 p0 = lds2(par + PAR_T2 + ch * 64 + tq * 16), p1 = lds2(par + PAR_T2 + ch * 64 + 64 + tq * 16);
      uint32_t* dst = g_row + rb * 2 * DM + cj * 128 + ln * 4;
      st_pairs(dst, ln_mod(x0, cm, ch_, cl, p0.x, p0.y), ln_mod(x1, cm, ch_, cl, p1.x, p1.y), tag);
      st_pairs(dst + DM, x0, x1, tag);
      __syncwarp();
    }
    PROF(8, ct == PT, 37); STAMP(9);
    uint32_t wd[64];
    const uint32_t wda = base + unit_of(FT_D, warp >> 1) + (warp & 1) * 8192 + frow * 128 + ((((ln >> 3) & 1) ^ (ln & 7)) << 4);
#define LOAD_WD(f) ldmatrix4t((wda ^ ((((f) >> 1) & 3) * 32)) + ((f) >> 3) * 4096 + ((f) & 1) * 2048, wd[4 * (f)], wd[4 * (f) + 1], wd[4 * (f) + 2], wd[4 * (f) + 3])
    if (!early) {
      if (b < NFFN) mbar_wait(bar_box + (warp >> 1) * 8, 0);
      LOAD_WF(0);
      __syncwarp();
      mbar_arrive_pred(bar_gate, lane0);
    }
    if (b < NFFN) {
      const uint32_t own = base + unit_of(FT_G, warp >> 1) + (warp & 1) * 8192;
      mbar_wait(bar_box + (4 + (warp >> 1)) * 8, 0);
      LOAD_WF(1);
      uint32_t* const ydst = ypart_slot(b, warp * 16 + (tq & 1) * 8 + g);
      PROF(8, ct == PT, 31); STAMP(10);
      bool wdok;
      {
        uint32_t n = 0;
        while (!(wdok = __all_sync(0xffffffffu, mbar_test(bar_box + (8 + (warp >> 1)) * 8, 0))) && !__all_sync(0xffffffffu, mbar_test(bar_sel, 0))) watchdog(n);
      }
      if (wdok) {
#pragma unroll
        for (int f = 0; f < 16; f++) LOAD_WD(f);
      }
      STAMP(11);
      mbar_wait(bar_sel, 0);
      PROF(8, ct == PT, 33); STAMP(12);
      float d[8][4];
#pragma unroll
      for (int i = 0; i < 4; i++) { d[i][0] = 0.f; d[i][1] = 0.f; d[i][2] = 0.f; d[i][3] = 0.f; }
#pragma unroll
      for (int ks = 0; ks < 8; ks++) {
        const uint2 hb = lds2(own + 256 + ks * 32 + tq * 8);
#pragma unroll
        for (int mt = 0; mt < 4; mt++) {
          const int r = ks * 16 + mt * 4;
          mma16816(d[mt], wf[r], wf[r + 1], wf[r + 2], wf[r + 3], hb.x, hb.y);
        }
      }
      sts2(own + (tq * 8 + g) * 8, __float_as_uint((tq & 2) ? ((tq & 1) ? d[1][2] : d[1][0]) : ((tq & 1) ? d[0][2] : d[0][0])),
           __float_as_uint((tq & 2) ? ((tq & 1) ? d[3][2] : d[3][0]) : ((tq & 1) ? d[2][2] : d[2][0])));
      bar_sync(1, 256);
      uint32_t ab[4];
      {
        float G = 0.f, U = 0.f;
        uint2 pv[8];
#pragma unroll
        for (int w8 = 0; w8 < 8; w8++) pv[w8] = lds2(base + ln * 8 + ((FT_G >> (w8 >> 1) * 4) & 15) * UNIT + (w8 & 1) * 8192);
#pragma unroll
        for (int w8 = 0; w8 < 8; w8 += 2) {
          G += __uint_as_float(pv[w8].x) + __uint_as_float(pv[w8 + 1].x);
          U += __uint_as_float(pv[w8].y) + __uint_as_float(pv[w8 + 1].y);
        }
        const float act = rbf(silu_f(rbf(G))) * rbf(U);
        const uint32_t pk = pack_bf(act, __shfl_down_sync(0xffffffffu, act, 1));
#pragma unroll
        for (int i = 0; i < 4; i++) ab[i] = __shfl_sync(0xffffffffu, pk, i * 8 + tq * 2);
      }
      if (!wdok) {
        mbar_wait(bar_box + (8 + (warp >> 1)) * 8, 0);
#pragma unroll
        for (int f = 0; f < 16; f++) LOAD_WD(f);
      }
      PROF(8, ct == PT, 34); STAMP(13);
#pragma unroll
      for (int mt = 0; mt < 8; mt++) {
        d[mt][0] = 0.f; d[mt][1] = 0.f; d[mt][2] = 0.f; d[mt][3] = 0.f;
        mma16816(d[mt], wd[mt * 8], wd[mt * 8 + 1], wd[mt * 8 + 2], wd[mt * 8 + 3], ab[0], ab[1]);
        mma16816(d[mt], wd[mt * 8 + 4], wd[mt * 8 + 5], wd[mt * 8 + 6], wd[mt * 8 + 7], ab[2], ab[3]);
      }
      uint32_t yw[4];
#pragma unroll
      for (int i = 0; i < 4; i++) yw[i] = (tq & 1) ? pack_bf(d[2 * i][2], d[2 * i + 1][2]) : pack_bf(d[2 * i][0], d[2 * i + 1][0]);
      if (tq < 2) st_b128(ydst, (yw[0] & ~1u) | (tag & 1), (yw[1] & ~1u) | (tag >> 1), yw[2], yw[3]);
      PROF(8, ct == PT, 35); STAMP(14);
    }
    mbar_wait(bar_sel, 0);
    mbar_arrive_pred(bar_win, ct == 0);
    const int iwin = lds1(par + PAR_CONST + 60) & 0x7ff;
    const bool cand = (iwin >> 4) == rb * 8 + warp;
    {
      const uint32_t mm0 = __shfl_sync(0xffffffffu, mm, ln & ~1), mm1 = __shfl_sync(0xffffffffu, mm, ln | 1);
      const uint32_t ih0 = __shfl_sync(0xffffffffu, ih, ln & ~1), ih1 = __shfl_sync(0xffffffffu, ih, ln | 1);
      const uint32_t il0 = __shfl_sync(0xffffffffu, il, ln & ~1), il1 = __shfl_sync(0xffffffffu, il, ln | 1);
#pragma unroll 1
      for (int hf = 0; hf < 2; hf++) {
        uint32_t x[16];
#pragma unroll
        for (int i = 0; i < 8; i += 2) ldmatrix4((trow ^ (i << 4)) + hf * 16384, x[2 * i], x[2 * i + 1], x[2 * i + 2], x[2 * i + 3]);
#pragma unroll
        for (int i = 0; i < 8; i++) {
          const uint4 pv = lds4(par + PAR_T2 + (hf * 8 + i) * 64 + tq * 16);
          x[2 * i] = hfma2(hfma2(ln_norm(x[2 * i], mm0, ih0, il0), pv.x, pv.y), pv.z, x[2 * i]);
          x[2 * i + 1] = hfma2(hfma2(ln_norm(x[2 * i + 1], mm1, ih1, il1), pv.x, pv.y), pv.z, x[2 * i + 1]);
        }
#pragma unroll
        for (int i = 0; i < 8; i += 2) stmatrix4((trow ^ (i << 4)) + hf * 16384, x[2 * i], x[2 * i + 1], x[2 * i + 2], x[2 * i + 3]);
        if (!cand) fence_async_smem();
        __syncwarp();
        if (!cand && elect_one()) {
          tma2d_store(&maps.out, res + hf * 16384 + warp * 2048, cj * 128 + hf * 64, rb * 128 + warp * 16);
          asm volatile("cp.async.bulk.commit_group;" ::: "memory");
        }
      }
    }
    if (cand) {
      const int wrow0 = warp * 16;
#pragma unroll 2
      for (int p = 0; p < 8; p++) {
        const int row = 2 * p + (ln >> 4), ch = ln & 15;
        const uint4 v = lds4(res + (ch >> 3) * 16384 + (wrow0 + row) * 128 + (((ch & 7) ^ (row & 7)) << 4));
        if (rb * 128 + wrow0 + row != iwin) *reinterpret_cast<uint4*>(P.out + (size_t)(rb * 128 + wrow0 + row) * DM + cj * 128 + ch * 8) = v;
      }
    }
    asm volatile("cp.async.bulk.wait_group.read 0;" ::: "memory");
    PROF(8, ct == PT, 11); STAMP(15);
    cluster_wait();
  }
}

typedef CUresult (*EncodeFn)(CUtensorMap*, CUtensorMapDataType, cuuint32_t, void*, const cuuint64_t*, const cuuint64_t*,
                             const cuuint32_t*, const cuuint32_t*, CUtensorMapInterleave, CUtensorMapSwizzle,
                             CUtensorMapL2promotion, CUtensorMapFloatOOBfill);

void map2d(EncodeFn enc, CUtensorMap* m, const void* p, uint64_t rows, uint64_t cols, uint32_t brows) {
  cuuint64_t dims[2] = {cols, rows}, strides[1] = {cols * 2};
  cuuint32_t box[2] = {64, brows}, es[2] = {1, 1};
  enc(m, CU_TENSOR_MAP_DATA_TYPE_BFLOAT16, 2, const_cast<void*>(p), dims, strides, box, es, CU_TENSOR_MAP_INTERLEAVE_NONE,
      CU_TENSOR_MAP_SWIZZLE_128B, CU_TENSOR_MAP_L2_PROMOTION_L2_256B, CU_TENSOR_MAP_FLOAT_OOB_FILL_NONE);
}
void map2d_narrow(EncodeFn enc, CUtensorMap* m, const void* p, uint64_t rows, uint64_t cols, uint32_t brows) {
  cuuint64_t dims[2] = {cols, rows}, strides[1] = {cols * 2};
  cuuint32_t box[2] = {32, brows}, es[2] = {1, 1};
  enc(m, CU_TENSOR_MAP_DATA_TYPE_BFLOAT16, 2, const_cast<void*>(p), dims, strides, box, es, CU_TENSOR_MAP_INTERLEAVE_NONE,
      CU_TENSOR_MAP_SWIZZLE_64B, CU_TENSOR_MAP_L2_PROMOTION_L2_64B, CU_TENSOR_MAP_FLOAT_OOB_FILL_NONE);
}
void map3d(EncodeFn enc, CUtensorMap* m, const void* p, uint64_t rows, uint64_t cols, uint32_t brows, uint32_t nch) {
  cuuint64_t dims[3] = {64, rows, cols / 64}, strides[2] = {cols * 2, 128};
  cuuint32_t box[3] = {64, brows, nch}, es[3] = {1, 1, 1};
  enc(m, CU_TENSOR_MAP_DATA_TYPE_BFLOAT16, 3, const_cast<void*>(p), dims, strides, box, es, CU_TENSOR_MAP_INTERLEAVE_NONE,
      CU_TENSOR_MAP_SWIZZLE_128B, CU_TENSOR_MAP_L2_PROMOTION_L2_256B, CU_TENSOR_MAP_FLOAT_OOB_FILL_NONE);
}

}

extern "C" void kernel_launch(void* const* d_in, const int* in_sizes, int n_in, void* d_out, int out_size) {
  (void)in_sizes; (void)n_in; (void)out_size;
  static EncodeFn enc = nullptr;
  if (!enc) {
    void* fn = nullptr;
    cudaDriverEntryPointQueryResult st;
    cudaGetDriverEntryPoint("cuTensorMapEncodeTiled", &fn, cudaEnableDefault, &st);
    enc = (EncodeFn)fn;
    cudaFuncSetAttribute(fused_kernel, cudaFuncAttributeMaxDynamicSharedMemorySize, SMEM_BYTES);
  }
  Maps maps;
  map2d(enc, &maps.x, d_in[0], SEQ, DM, 128);
  map2d(enc, &maps.out, d_out, SEQ, DM, 16);
  map3d(enc, &maps.wq, d_in[3], DM, NQ, 64, 2);
  map3d(enc, &maps.k, d_in[1], 4 * SK, 128, 128, 1);
  map3d(enc, &maps.v, d_in[2], 4 * SK, 128, 128, 1);
  map3d(enc, &maps.wo, d_in[4], NQ, DM, 64, 2);
  map2d_narrow(enc, &maps.wg, d_in[7], DM, FF, 256);
  map2d_narrow(enc, &maps.wu, d_in[8], DM, FF, 256);
  map3d(enc, &maps.wd, d_in[9], FF, DM, 32, 4);
  map2d_narrow(enc, &maps.wm, d_in[11], DM, NMOD, 256);
  Ptrs p;
  p.x = (const __nv_bfloat16*)d_in[0];
  p.w_r = (const __nv_bfloat16*)d_in[6];
  p.w_gate = (const __nv_bfloat16*)d_in[7];
  p.w_up = (const __nv_bfloat16*)d_in[8];
  p.w_down = (const __nv_bfloat16*)d_in[9];
  p.c = (const __nv_bfloat16*)d_in[10];
  p.w_mod = (const __nv_bfloat16*)d_in[11];
  p.out = (__nv_bfloat16*)d_out;
  fused_kernel<<<NMAIN + NHELP, 384, SMEM_BYTES>>>(maps, p);
}
```

```cpp
#include <cuda_runtime.h>
#include <cuda_bf16.h>
#include <cuda.h>
#include <stdint.h>
#include <type_traits>

#define HD 2
#define HDX 2
#define NRS 8
#define OSL 900
#define OSL2 400
#define RSL 40
#define BIAS 96.f
#define N1L 1
#define C1 1
#define VREL 5
#define OPS 8192
#define ODS1 5
#define ODS 7
#define PG0 15
#define WB 2
#define WN 20
#define HU 32
#define RES0 17
#define RES1 20
#define GOST 20
#define NS1 5
#define LD2 4
#define FPACE0 2
#define FPACE 3
#define CR 8
#define CS 8

namespace {

constexpr int SEQ = 2048, DM = 1024, NQ = 4096, SK = 2048, WIN = 512, FF = 3584, NMOD = 6144;
constexpr int NMAIN = 128, NHELP = 4, NFFN = 112;
constexpr int NSLOT = 4, SLOT_BYTES = 32768, UNIT = 16384, GST_BYTES = 3 * UNIT;
constexpr uint32_t XT1 = 0xDCBA, XT2 = 0x9687;
constexpr uint32_t WT0 = 0xA741, WT1 = 0x7420, WT2 = 0x4A20;
constexpr uint32_t AT0 = WT1, AT1 = WT2;
constexpr uint32_t QT = 0xDC9696DC;
constexpr int OFF_STAGE = 12 * UNIT;
constexpr uint32_t FT_G = 0x07B3, FT_U = 0xA628, FT_D = 0x5149;
constexpr int OFF_RES = 12 * UNIT;
constexpr int OFF_PAR = 14 * UNIT;
constexpr int OFF_BAR = OFF_PAR + 2528;
constexpr int SMEM_BYTES = OFF_BAR + 544;
static_assert(SMEM_BYTES <= 232448, "smem");

constexpr int PAR_T1 = 0;
constexpr int PAR_T2 = 512;
constexpr int PAR_CONST = 1536;
constexpr int PAR_RED = 1600;
constexpr int PAR_SINK = 2176;

struct Maps {
  CUtensorMap x, wq, k, v, wo, wg, wu, wd, wm, out;
};
struct Ptrs {
  const __nv_bfloat16 *x, *w_r, *c, *w_mod, *w_gate, *w_up, *w_down;
  __nv_bfloat16* out;
};

__device__ __align__(1024) uint8_t g_act[16 * 80 * UNIT];
__device__ __align__(128) uint32_t g_mod[NMOD];
__device__ __align__(128) uint32_t g_modp[2 * 2 * DM];
__device__ __align__(128) uint32_t g_ln1[SEQ * 4];
__device__ __align__(128) uint32_t g_cnt_h[16 * 32];
__device__ __align__(128) uint32_t g_cnt_o[128 * 32];
__device__ __align__(128) uint32_t g_xch[NMAIN * 8 * 256 * 4];
__device__ __align__(128) uint32_t g_stats[8 * SEQ * 4];
__device__ __align__(128) uint32_t g_cand[CR * 512];
__device__ __align__(128) uint32_t g_row[16 * 2 * DM];
__device__ __align__(128) uint32_t g_ypart[NMAIN * NFFN * 4];
__device__ __forceinline__ uint32_t* ypart_slot(int writer, int reader) { return g_ypart + (writer * NMAIN + reader) * 4; }
__device__ uint32_t g_epoch;

__device__ __forceinline__ uint32_t fresh_lane() { uint32_t l; asm volatile("mov.u32 %0, %%laneid;" : "=r"(l)); return l; }
__device__ __forceinline__ uint32_t frag_offset(int warp) {
  const uint32_t l = fresh_lane();
  return ((warp & 3) * 16 + (l & 15)) * 128 + (((l >> 4) ^ (l & 7)) << 4);
}
__device__ __forceinline__ bool elect_one() {
  uint32_t p;
  asm volatile("{ .reg .pred q; elect.sync _|q, 0xffffffff; selp.u32 %0, 1, 0, q; }" : "=r"(p));
  return p;
}
__device__ __forceinline__ uint32_t smem_u32(const void* p) { return (uint32_t)__cvta_generic_to_shared(p); }
__device__ __forceinline__ void mbar_init(uint32_t bar, uint32_t cnt) {
  asm volatile("mbarrier.init.shared::cta.b64 [%0], %1;" ::"r"(bar), "r"(cnt) : "memory");
}
__device__ __forceinline__ void mbar_expect_tx(uint32_t bar, uint32_t bytes) {
  asm volatile("mbarrier.arrive.expect_tx.shared::cta.b64 _, [%0], %1;" ::"r"(bar), "r"(bytes) : "memory");
}
__device__ __forceinline__ void mbar_arrive(uint32_t bar) {
  asm volatile("mbarrier.arrive.shared::cta.b64 _, [%0];" ::"r"(bar) : "memory");
}
__device__ __forceinline__ void mbar_arrive_pred(uint32_t bar, bool p) {
  asm volatile("{ .reg .pred p; setp.ne.b32 p, %1, 0; @p mbarrier.arrive.shared::cta.b64 _, [%0]; }" ::"r"(bar), "r"((int)p) : "memory");
}
__device__ __forceinline__ void mbar_arrive_cl(uint32_t bar, uint32_t off, bool p = true) {
  asm volatile("{ .reg .pred p, q; .reg .b32 a; setp.ne.b32 q, %2, 0; setp.ne.and.b32 p, %0, 0, q; add.u32 a, %0, %1; @p mbarrier.arrive.shared::cluster.b64 _, [a]; }"
               ::"r"(bar), "r"(off), "r"((int)p) : "memory");
}
__device__ __forceinline__ uint32_t mapa(uint32_t addr, uint32_t cta) {
  uint32_t r; asm("mapa.shared::cluster.u32 %0, %1, %2;" : "=r"(r) : "r"(addr), "r"(cta)); return r;
}
__device__ __forceinline__ void cluster_arrive() { asm volatile("barrier.cluster.arrive.relaxed.aligned;" ::: "memory"); }
__device__ __forceinline__ void cluster_wait() { asm volatile("barrier.cluster.wait.aligned;" ::: "memory"); }
__device__ __forceinline__ void watchdog(uint32_t& n) {
}
__device__ __forceinline__ void mbar_wait(uint32_t bar, uint32_t parity) {
  asm volatile("{\n.reg .pred p;\nWAIT_%=:\nmbarrier.try_wait.parity.shared::cta.b64 p, [%0], %1;\n@!p bra WAIT_%=;\n}" ::"r"(bar), "r"(parity) : "memory");
}
__device__ __forceinline__ bool mbar_test(uint32_t bar, uint32_t parity) {
  uint32_t ok;
  asm volatile("{\n.reg .pred p;\nmbarrier.test_wait.parity.shared::cta.b64 p, [%1], %2;\nselp.u32 %0, 1, 0, p;\n}" : "=r"(ok) : "r"(bar), "r"(parity) : "memory");
  return ok;
}
__device__ __forceinline__ uint64_t l2_stream() {
  uint64_t f; asm("createpolicy.fractional.L2::evict_first.b64 %0, 1.0;" : "=l"(f)); return f;
}
__device__ __forceinline__ uint64_t l2_normal() {
  uint64_t f; asm("createpolicy.fractional.L2::evict_normal.b64 %0, 1.0;" : "=l"(f)); return f;
}
__device__ __forceinline__ void tma2d(uint32_t dst, const CUtensorMap* m, int c0, int c1, uint32_t bar) {
  asm volatile("cp.async.bulk.tensor.2d.shared::cluster.global.mbarrier::complete_tx::bytes.L2::cache_hint [%0], [%1, {%3, %4}], [%2], %5;"
               ::"r"(dst), "l"(m), "r"(bar), "r"(c0), "r"(c1), "l"(l2_stream()) : "memory");
}
__device__ __forceinline__ void bulk_load(uint32_t dst, const void* src, uint32_t bytes, uint32_t bar) {
  asm volatile("cp.async.bulk.shared::cluster.global.mbarrier::complete_tx::bytes [%0], [%1], %2, [%3];" ::"r"(dst), "l"(src), "r"(bytes), "r"(bar) : "memory");
}
__device__ __forceinline__ void bulk_load_stream(uint32_t dst, const void* src, uint32_t bytes, uint32_t bar, uint64_t pol = l2_stream()) {
  asm volatile("cp.async.bulk.shared::cluster.global.mbarrier::complete_tx::bytes.L2::cache_hint [%0], [%1], %2, [%3], %4;"
               ::"r"(dst), "l"(src), "r"(bytes), "r"(bar), "l"(pol) : "memory");
}
__device__ __forceinline__ void tma2d_store(const CUtensorMap* m, uint32_t src, int c0, int c1) {
  asm volatile("cp.async.bulk.tensor.2d.global.shared::cta.bulk_group [%0, {%2, %3}], [%1];" ::"l"(m), "r"(src), "r"(c0), "r"(c1) : "memory");
}
__device__ __forceinline__ void bulk_store(void* dst, uint32_t src, uint32_t bytes) {
  asm volatile("cp.async.bulk.global.shared::cta.bulk_group [%0], [%1], %2;" ::"l"(dst), "r"(src), "r"(bytes) : "memory");
}
__device__ __forceinline__ int slice_of(int i) { return i + ((i & 7) == 1) - ((i & 7) == 2); }
__device__ __forceinline__ uint32_t unit_of(uint32_t table, uint32_t i) { return ((table >> (i * 4)) & 15) * UNIT; }
__device__ __forceinline__ void tma3d(uint32_t dst, const CUtensorMap* m, int c0, int c1, int c2, uint32_t bar) {
  asm volatile("cp.async.bulk.tensor.3d.shared::cluster.global.mbarrier::complete_tx::bytes.L2::cache_hint [%0], [%1, {%3, %4, %5}], [%2], %6;"
               ::"r"(dst), "l"(m), "r"(bar), "r"(c0), "r"(c1), "r"(c2), "l"(l2_stream()) : "memory");
}
template <bool STREAM>
__device__ __forceinline__ void tma3d_mc(uint32_t dst, const CUtensorMap* m, int c0, int c1, int c2, uint32_t bar) {
  if (STREAM)
    asm volatile("cp.async.bulk.tensor.3d.shared::cluster.global.mbarrier::complete_tx::bytes.multicast::cluster.L2::cache_hint [%0], [%1, {%3, %4, %5}], [%2], %6, %7;"
                 ::"r"(dst), "l"(m), "r"(bar), "r"(c0), "r"(c1), "r"(c2), "h"((uint16_t)3), "l"(l2_stream()) : "memory");
  else
    asm volatile("cp.async.bulk.tensor.3d.shared::cluster.global.mbarrier::complete_tx::bytes.multicast::cluster [%0], [%1, {%3, %4, %5}], [%2], %6;"
                 ::"r"(dst), "l"(m), "r"(bar), "r"(c0), "r"(c1), "r"(c2), "h"((uint16_t)3) : "memory");
}
__device__ __forceinline__ void prefetch_map(const CUtensorMap* m) {
  asm volatile("prefetch.tensormap [%0];" ::"l"(m) : "memory");
}
__device__ __forceinline__ void fence_async() { asm volatile("fence.proxy.async.global;" ::: "memory"); }
__device__ __forceinline__ void fence_async_smem() { asm volatile("fence.proxy.async.shared::cta;" ::: "memory"); }
__device__ __forceinline__ void bar_sync(int id, int n) { asm volatile("bar.sync %0, %1;" ::"r"(id), "r"(n) : "memory"); }
__device__ __forceinline__ void bar_arrive(int id, int n) { asm volatile("bar.arrive %0, %1;" ::"r"(id), "r"(n) : "memory"); }
__device__ __forceinline__ void wg_fence() { asm volatile("wgmma.fence.sync.aligned;" ::: "memory"); }
__device__ __forceinline__ void wg_commit() { asm volatile("wgmma.commit_group.sync.aligned;" ::: "memory"); }
template <int N> __device__ __forceinline__ void wg_wait() { asm volatile("wgmma.wait_group.sync.aligned %0;" ::"n"(N) : "memory"); }
__device__ __forceinline__ uint64_t make_desc(uint32_t addr, uint32_t lbo, uint32_t sbo) {
  return (uint64_t)((addr & 0x3FFFF) >> 4) | ((uint64_t)(lbo >> 4) << 16) | ((uint64_t)(sbo >> 4) << 32) | (1ull << 62);
}
__device__ __forceinline__ uint32_t ld_relaxed(const uint32_t* p) {
  uint32_t v; asm volatile("ld.relaxed.gpu.global.u32 %0, [%1];" : "=r"(v) : "l"(p) : "memory"); return v;
}
__device__ __forceinline__ uint32_t ld_acquire(const uint32_t* p) {
  uint32_t v; asm volatile("ld.acquire.gpu.global.u32 %0, [%1];" : "=r"(v) : "l"(p) : "memory"); return v;
}
__device__ __forceinline__ uint4 ld_relaxed4(const uint32_t* p) {
  uint4 v; asm volatile("ld.relaxed.gpu.global.v4.u32 {%0,%1,%2,%3}, [%4];" : "=r"(v.x), "=r"(v.y), "=r"(v.z), "=r"(v.w) : "l"(p) : "memory"); return v;
}
__device__ __forceinline__ void st_relaxed(uint32_t* p, uint32_t v) {
  asm volatile("st.relaxed.gpu.global.u32 [%0], %1;" ::"l"(p), "r"(v) : "memory");
}
__device__ __forceinline__ void st_relaxed4(uint32_t* p, uint32_t a, uint32_t b, uint32_t c, uint32_t d) {
  asm volatile("st.relaxed.gpu.global.v4.u32 [%0], {%1,%2,%3,%4};" ::"l"(p), "r"(a), "r"(b), "r"(c), "r"(d) : "memory");
}
__device__ __forceinline__ void st_b128(uint32_t* p, uint32_t a, uint32_t b, uint32_t c, uint32_t d) {
  asm volatile("{ .reg .b64 u, v; .reg .b128 w; mov.b64 u, {%1, %2}; mov.b64 v, {%3, %4}; mov.b128 w, {u, v}; st.relaxed.gpu.global.b128 [%0], w; }"
               ::"l"(p), "r"(a), "r"(b), "r"(c), "r"(d) : "memory");
}
__device__ __forceinline__ uint4 ld_b128(const uint32_t* p) {
  uint4 r;
  asm volatile("{ .reg .b64 u, v; .reg .b128 w; ld.relaxed.gpu.global.b128 w, [%4]; mov.b128 {u, v}, w; mov.b64 {%0, %1}, u; mov.b64 {%2, %3}, v; }"
               : "=r"(r.x), "=r"(r.y), "=r"(r.z), "=r"(r.w) : "l"(p) : "memory");
  return r;
}
__device__ __forceinline__ void st_pairs(uint32_t* p, uint32_t a, uint32_t b, uint32_t tag) {
  asm volatile("{ .reg .b64 u, v; mov.b64 u, {%1, %3}; mov.b64 v, {%2, %3}; st.relaxed.gpu.global.v2.b64 [%0], {u, v}; }"
               ::"l"(p), "r"(a), "r"(b), "r"(tag) : "memory");
}
__device__ __forceinline__ uint4 ld_pairs(const uint32_t* p) {
  uint4 v;
  asm volatile("{ .reg .b64 u, v; ld.relaxed.gpu.global.v2.b64 {u, v}, [%4]; mov.b64 {%0, %1}, u; mov.b64 {%2, %3}, v; }"
               : "=r"(v.x), "=r"(v.y), "=r"(v.z), "=r"(v.w) : "l"(p) : "memory");
  return v;
}
__device__ __forceinline__ uint2 ld_pair(const uint32_t* p) {
  uint2 v;
  asm volatile("{ .reg .b64 u; ld.relaxed.gpu.global.b64 u, [%2]; mov.b64 {%0, %1}, u; }" : "=r"(v.x), "=r"(v.y) : "l"(p) : "memory");
  return v;
}
__device__ __forceinline__ void red_release(uint32_t* p, uint32_t v) {
  asm volatile("red.release.gpu.global.add.u32 [%0], %1;" ::"l"(p), "r"(v) : "memory");
}
__device__ __forceinline__ uint32_t ldg_nc1(const void* p) {
  uint32_t v;
  asm volatile("ld.global.nc.u32 %0, [%1];" : "=r"(v) : "l"(p));
  return v;
}
__device__ __forceinline__ uint4 ldg_nc4(const void* p) {
  uint4 v; asm volatile("ld.global.nc.L1::no_allocate.v4.u32 {%0,%1,%2,%3}, [%4];" : "=r"(v.x), "=r"(v.y), "=r"(v.z), "=r"(v.w) : "l"(p)); return v;
}
__device__ __forceinline__ uint4 ldg_stream4(const void* p) {
  uint4 v;
  asm volatile("ld.global.nc.L1::no_allocate.L2::cache_hint.v4.u32 {%0,%1,%2,%3}, [%4], %5;" : "=r"(v.x), "=r"(v.y), "=r"(v.z), "=r"(v.w) : "l"(p), "l"(l2_stream()));
  return v;
}
__device__ __forceinline__ void stg4(void* p, uint4 v) {
  asm volatile("st.global.v4.u32 [%0], {%1,%2,%3,%4};" ::"l"(p), "r"(v.x), "r"(v.y), "r"(v.z), "r"(v.w) : "memory");
}
__device__ __forceinline__ void wait_counter(const uint32_t* p, uint32_t target) {
  uint32_t n = 0;
  while (__any_sync(0xffffffffu, (int)(ld_acquire(p) - target) < 0)) { watchdog(n); }
}
__device__ __forceinline__ uint32_t tagf(float v, uint32_t tag) { return (__float_as_uint(v) & ~3u) | tag; }
__device__ __forceinline__ bool tag_ok(uint4 v, uint32_t tag) { return (((v.x ^ tag) | (v.y ^ tag) | (v.z ^ tag) | (v.w ^ tag)) & 3u) == 0; }
__device__ __forceinline__ float untag_sum(uint32_t a, uint32_t b) { return __uint_as_float(a & ~3u) + __uint_as_float(b & ~3u); }
__device__ __forceinline__ uint4 poll4(const uint32_t* p, uint32_t tag) {
  uint4 v = ld_relaxed4(p);
  uint32_t n = 0;
  while (!__all_sync(0xffffffffu, tag_ok(v, tag))) { v = ld_relaxed4(p); watchdog(n); }
  return v;
}
__device__ __forceinline__ float bf_lo(uint32_t v) { return __uint_as_float(v << 16); }
__device__ __forceinline__ float bf_hi(uint32_t v) { return __uint_as_float(v & 0xffff0000u); }
__device__ __forceinline__ uint32_t pack_bf(float lo, float hi) {
  uint32_t r; asm("cvt.rn.bf16x2.f32 %0, %1, %2;" : "=r"(r) : "f"(hi), "f"(lo)); return r;
}
__device__ __forceinline__ float rbf(float v) { return __uint_as_float(pack_bf(0.f, v) & 0xffff0000u); }
__device__ __forceinline__ uint32_t hmul2(uint32_t a, uint32_t b) {
  uint32_t r; asm("mul.rn.bf16x2 %0, %1, %2;" : "=r"(r) : "r"(a), "r"(b)); return r;
}
__device__ __forceinline__ uint32_t hadd2(uint32_t a, uint32_t b) {
  uint32_t r; asm("add.rn.bf16x2 %0, %1, %2;" : "=r"(r) : "r"(a), "r"(b)); return r;
}
__device__ __forceinline__ uint32_t hsub2(uint32_t a, uint32_t b) {
  uint32_t r; asm("sub.rn.bf16x2 %0, %1, %2;" : "=r"(r) : "r"(a), "r"(b)); return r;
}
__device__ __forceinline__ float rcp(float x) { float r; asm("rcp.approx.ftz.f32 %0, %1;" : "=f"(r) : "f"(x)); return r; }
__device__ __forceinline__ float ex2(float x) { float r; asm("ex2.approx.ftz.f32 %0, %1;" : "=f"(r) : "f"(x)); return r; }
__device__ __forceinline__ void stmatrix4(uint32_t addr, uint32_t a, uint32_t b, uint32_t c, uint32_t d) {
  asm volatile("stmatrix.sync.aligned.m8n8.x4.shared.b16 [%0], {%1,%2,%3,%4};" ::"r"(addr), "r"(a), "r"(b), "r"(c), "r"(d) : "memory");
}
__device__ __forceinline__ void ldmatrix4(uint32_t addr, uint32_t& a, uint32_t& b, uint32_t& c, uint32_t& d) {
  asm volatile("ldmatrix.sync.aligned.m8n8.x4.shared.b16 {%0,%1,%2,%3}, [%4];" : "=r"(a), "=r"(b), "=r"(c), "=r"(d) : "r"(addr) : "memory");
}
__device__ __forceinline__ void ldmatrix4t(uint32_t addr, uint32_t& a, uint32_t& b, uint32_t& c, uint32_t& d) {
  asm volatile("ldmatrix.sync.aligned.m8n8.x4.trans.shared.b16 {%0,%1,%2,%3}, [%4];" : "=r"(a), "=r"(b), "=r"(c), "=r"(d) : "r"(addr) : "memory");
}
__device__ __forceinline__ void mma16816(float (&d)[4], uint32_t a0, uint32_t a1, uint32_t a2, uint32_t a3, uint32_t b0, uint32_t b1) {
  asm volatile("mma.sync.aligned.m16n8k16.row.col.f32.bf16.bf16.f32 {%0,%1,%2,%3}, {%4,%5,%6,%7}, {%8,%9}, {%0,%1,%2,%3};"
               : "+f"(d[0]), "+f"(d[1]), "+f"(d[2]), "+f"(d[3]) : "r"(a0), "r"(a1), "r"(a2), "r"(a3), "r"(b0), "r"(b1));
}
__device__ __forceinline__ void sts1(uint32_t a, uint32_t v) { asm volatile("st.shared.u32 [%0], %1;" ::"r"(a), "r"(v) : "memory"); }
__device__ __forceinline__ uint4 lds4(uint32_t a) {
  uint4 v; asm volatile("ld.shared.v4.u32 {%0,%1,%2,%3}, [%4];" : "=r"(v.x), "=r"(v.y), "=r"(v.z), "=r"(v.w) : "r"(a) : "memory"); return v;
}
__device__ __forceinline__ uint2 lds2(uint32_t a) {
  uint2 v; asm volatile("ld.shared.v2.u32 {%0,%1}, [%2];" : "=r"(v.x), "=r"(v.y) : "r"(a) : "memory"); return v;
}
__device__ __forceinline__ uint32_t lds1(uint32_t a) {
  uint32_t v; asm volatile("ld.shared.u32 %0, [%1];" : "=r"(v) : "r"(a) : "memory"); return v;
}
__device__ __forceinline__ void sts2(uint32_t a, uint32_t x, uint32_t y) { asm volatile("st.shared.v2.u32 [%0], {%1,%2};" ::"r"(a), "r"(x), "r"(y) : "memory"); }
__device__ __forceinline__ void sts4(uint32_t a, uint4 v) {
  asm volatile("st.shared.v4.u32 [%0], {%1,%2,%3,%4};" ::"r"(a), "r"(v.x), "r"(v.y), "r"(v.z), "r"(v.w) : "memory");
}
__device__ __forceinline__ float silu_f(float v) { return __fdividef(v, 1.f + __expf(-v)); }
__device__ __forceinline__ uint32_t hfma2(uint32_t a, uint32_t b, uint32_t c) {
  uint32_t r; asm("fma.rn.bf16x2 %0, %1, %2, %3;" : "=r"(r) : "r"(a), "r"(b), "r"(c)); return r;
}
__device__ __forceinline__ void split_inv(float sd, uint32_t& ih, uint32_t& il) {
  const float inv = rcp(sd);
  ih = pack_bf(inv, inv);
  const float lo = inv - bf_lo(ih);
  il = pack_bf(lo, lo);
}
__device__ __forceinline__ uint32_t ln_norm(uint32_t x, uint32_t mean2, uint32_t ih, uint32_t il) {
  const uint32_t d = hsub2(x, mean2);
  return hfma2(d, ih, hmul2(d, il));
}
__device__ __forceinline__ uint32_t ln_mod(uint32_t x, uint32_t mean2, uint32_t ih, uint32_t il, uint32_t c1, uint32_t sh) {
  return hadd2(hmul2(ln_norm(x, mean2, ih, il), c1), sh);
}

#define R8(a, i) "+f"(a[i]), "+f"(a[i + 1]), "+f"(a[i + 2]), "+f"(a[i + 3]), "+f"(a[i + 4]), "+f"(a[i + 5]), "+f"(a[i + 6]), "+f"(a[i + 7])
#define D64 "{%0,%1,%2,%3,%4,%5,%6,%7,%8,%9,%10,%11,%12,%13,%14,%15,%16,%17,%18,%19,%20,%21,%22,%23,%24,%25,%26,%27,%28,%29,%30,%31," \
            "%32,%33,%34,%35,%36,%37,%38,%39,%40,%41,%42,%43,%44,%45,%46,%47,%48,%49,%50,%51,%52,%53,%54,%55,%56,%57,%58,%59,%60,%61,%62,%63}"
template <int TB>
__device__ __forceinline__ void mma_ss(float (&d)[64], uint64_t da, uint64_t db, int sc) {
  asm volatile("{\n.reg .pred p;\nsetp.ne.b32 p, %66, 0;\n"
               "wgmma.mma_async.sync.aligned.m64n128k16.f32.bf16.bf16 " D64 ", %64, %65, p, 1, 1, 0, %67;\n}"
               : R8(d, 0), R8(d, 8), R8(d, 16), R8(d, 24), R8(d, 32), R8(d, 40), R8(d, 48), R8(d, 56)
               : "l"(da), "l"(db), "r"(sc), "n"(TB));
}
template <int TB>
__device__ __forceinline__ void mma_rs(float (&d)[64], uint32_t a0, uint32_t a1, uint32_t a2, uint32_t a3, uint64_t db, int sc) {
  asm volatile("{\n.reg .pred p;\nsetp.ne.b32 p, %69, 0;\n"
               "wgmma.mma_async.sync.aligned.m64n128k16.f32.bf16.bf16 " D64 ", {%64,%65,%66,%67}, %68, p, 1, 1, %70;\n}"
               : R8(d, 0), R8(d, 8), R8(d, 16), R8(d, 24), R8(d, 32), R8(d, 40), R8(d, 48), R8(d, 56)
               : "r"(a0), "r"(a1), "r"(a2), "r"(a3), "l"(db), "r"(sc), "n"(TB));
}
#define D128 "{%0,%1,%2,%3,%4,%5,%6,%7,%8,%9,%10,%11,%12,%13,%14,%15,%16,%17,%18,%19,%20,%21,%22,%23,%24,%25,%26,%27,%28,%29,%30,%31," \
             "%32,%33,%34,%35,%36,%37,%38,%39,%40,%41,%42,%43,%44,%45,%46,%47,%48,%49,%50,%51,%52,%53,%54,%55,%56,%57,%58,%59,%60,%61,%62,%63," \
             "%64,%65,%66,%67,%68,%69,%70,%71,%72,%73,%74,%75,%76,%77,%78,%79,%80,%81,%82,%83,%84,%85,%86,%87,%88,%89,%90,%91,%92,%93,%94,%95," \
             "%96,%97,%98,%99,%100,%101,%102,%103,%104,%105,%106,%107,%108,%109,%110,%111,%112,%113,%114,%115,%116,%117,%118,%119,%120,%121,%122,%123,%124,%125,%126,%127}"
#define R128(d, e) R8(d, 0), R8(d, 8), R8(d, 16), R8(d, 24), R8(d, 32), R8(d, 40), R8(d, 48), R8(d, 56), \
                   R8(e, 0), R8(e, 8), R8(e, 16), R8(e, 24), R8(e, 32), R8(e, 40), R8(e, 48), R8(e, 56)
__device__ __forceinline__ void mma256_ss(float (&d)[64], float (&e)[64], uint64_t da, uint64_t db, int sc) {
  asm volatile("{\n.reg .pred p;\nsetp.ne.b32 p, %130, 0;\n"
               "wgmma.mma_async.sync.aligned.m64n256k16.f32.bf16.bf16 " D128 ", %128, %129, p, 1, 1, 0, 1;\n}"
               : R128(d, e) : "l"(da), "l"(db), "r"(sc));
}
__device__ __forceinline__ void mma256_rs(float (&d)[64], float (&e)[64], uint32_t a0, uint32_t a1, uint32_t a2, uint32_t a3, uint64_t db) {
  asm volatile("{\n.reg .pred p;\nsetp.ne.b32 p, 1, 0;\n"
               "wgmma.mma_async.sync.aligned.m64n256k16.f32.bf16.bf16 " D128 ", {%128,%129,%130,%131}, %132, p, 1, 1, 1;\n}"
               : R128(d, e) : "r"(a0), "r"(a1), "r"(a2), "r"(a3), "l"(db));
}
template <int N> __device__ __forceinline__ void keep(float (&a)[N]) {
#pragma unroll
  for (int i = 0; i < N; i++) asm volatile("" : "+f"(a[i])::"memory");
}
template <int N> __device__ __forceinline__ void keep(uint32_t (&a)[N]) {
#pragma unroll
  for (int i = 0; i < N; i++) asm volatile("" : "+r"(a[i])::"memory");
}

#define STAMP(idx) do {} while (0)
#define PROF(grp, cond, idx) do {} while (0)

constexpr float SCL2 = 1.4426950408889634f * 0.08838834764831845f;

__device__ __forceinline__ void pack_p(const float (&s)[64], uint32_t (&p)[32]) {
#pragma unroll
  for (int i = 0; i < 32; i++) p[i] = pack_bf(s[2 * i], s[2 * i + 1]);
}

__device__ __forceinline__ void issue_qk(float (&s)[64], uint32_t q0, uint32_t q1, uint32_t kslot) {
  const uint64_t db = make_desc(kslot, 16, 1024), da0 = make_desc(q0, 16, 1024), da1 = make_desc(q1, 16, 1024);
#pragma unroll
  for (int kk = 0; kk < 8; kk++) mma_ss<0>(s, (kk < 4 ? da0 : da1) + (kk & 3) * 2, db + (kk >> 2) * 1024 + (kk & 3) * 2, kk != 0);
}
__device__ __forceinline__ void issue_pv(float (&o)[64], uint32_t (&p)[32], uint32_t vslot, int acc) {
  uint64_t db = make_desc(vslot, 16384, 1024);
#pragma unroll
  for (int kk = 0; kk < 8; kk++)
    mma_rs<1>(o, p[4 * kk], p[4 * kk + 1], p[4 * kk + 2], p[4 * kk + 3], db + kk * 128, kk == 0 ? acc : 1);
}

template <int H>
__device__ __forceinline__ void store_chunk(const float (&a)[64], uint32_t addr) {
#pragma unroll
  for (int i = 8 * H; i < 8 * H + 8; i += 2)
    stmatrix4(addr ^ ((i & 7) << 4), pack_bf(a[4 * i], a[4 * i + 1]), pack_bf(a[4 * i + 2], a[4 * i + 3]),
              pack_bf(a[4 * i + 4], a[4 * i + 5]), pack_bf(a[4 * i + 6], a[4 * i + 7]));
}
template <int H>
__device__ __forceinline__ void store_chunk(const float (&a)[64], float i0, float i1, uint32_t addr) {
#pragma unroll
  for (int i = 8 * H; i < 8 * H + 8; i += 2)
    stmatrix4(addr ^ ((i & 7) << 4), pack_bf(a[4 * i] * i0, a[4 * i + 1] * i0), pack_bf(a[4 * i + 2] * i1, a[4 * i + 3] * i1),
              pack_bf(a[4 * i + 4] * i0, a[4 * i + 5] * i0), pack_bf(a[4 * i + 6] * i1, a[4 * i + 7] * i1));
}
__device__ __forceinline__ float inv_quad_sum(float l) {
  l += __shfl_xor_sync(0xffffffffu, l, 1);
  l += __shfl_xor_sync(0xffffffffu, l, 2);
  return rcp(l);
}

__device__ __forceinline__ void write_table(uint32_t table, bool ca, uint32_t t, const uint4& m0, const uint4& m1) {
  float c0 = untag_sum(m0.x, m1.x), c1 = untag_sum(m0.y, m1.y), c2 = untag_sum(m0.z, m1.z), c3 = untag_sum(m0.w, m1.w);
  if (ca) { c0 = 1.f + rbf(c0); c1 = 1.f + rbf(c1); c2 = 1.f + rbf(c2); c3 = 1.f + rbf(c3); }
  const uint32_t d = table + (t >> 2) * 64 + (t & 1) * 32 + (t & 2) * 2 + (ca ? 0 : 8);
  sts1(d, pack_bf(c0, c1));
  sts1(d + 16, pack_bf(c2, c3));
}

__device__ __forceinline__ void ln_scalars(float mean, float var, float& mb, float& sd) {
  mb = rbf(mean);
  float r; asm("sqrt.approx.ftz.f32 %0, %1;" : "=f"(r) : "f"(rbf(rbf(var) + 1e-5f)));
  sd = rbf(r);
}

__global__ void __cluster_dims__(2, 1, 1) __launch_bounds__(384, 1) fused_kernel(const __grid_constant__ Maps maps, const Ptrs P) {
  extern __shared__ __align__(1024) uint8_t smem_raw[];
  const uint32_t base = smem_u32(smem_raw);
  const int tid = threadIdx.x, lane = tid & 31;
  const int warp = __shfl_sync(0xffffffffu, tid >> 5, 0);
  int b = blockIdx.x;
  if (b < NMAIN) {
    const int p = b >> 1;
    const int grp = p < 4 ? 7 : (p < 36 ? (p + 2) & 7 : (p - 30) % 7), k = p < 4 ? 4 + p : (p < 36 ? (p - 4) >> 3 : 4 + (p - 36) / 7);
    b = grp << 4 | k << 1 | (b & 1);
  }
  PROF(31, tid == 0, 0);

  if (b >= NMAIN) {
    float* sc = reinterpret_cast<float*>(smem_raw);
    float* red = sc + DM;
    for (int k = tid; k < DM; k += 384) sc[k] = rbf(silu_f(__bfloat162float(P.c[k])));
    __syncthreads();
    if (tid < 256) {
      const int col = 2048 + (b - NMAIN) * 1024 + (tid & 127) * 8, r0 = (tid >> 7) * 512;
      float acc[8];
#pragma unroll
      for (int e = 0; e < 8; e++) acc[e] = 0.f;
#pragma unroll 1
      for (int r = r0; r < r0 + 512; r += HU) {
        uint4 w[HU];
#pragma unroll
        for (int u = 0; u < HU; u++) w[u] = ldg_stream4(P.w_mod + (size_t)(r + u) * NMOD + col);
#pragma unroll
        for (int u = 0; u < HU; u++) {
          float s = sc[r + u];
          acc[0] += s * bf_lo(w[u].x); acc[1] += s * bf_hi(w[u].x); acc[2] += s * bf_lo(w[u].y); acc[3] += s * bf_hi(w[u].y);
          acc[4] += s * bf_lo(w[u].z); acc[5] += s * bf_hi(w[u].z); acc[6] += s * bf_lo(w[u].w); acc[7] += s * bf_hi(w[u].w);
        }
      }
      if (tid >= 128) {
#pragma unroll
        for (int e = 0; e < 8; e++) red[(tid & 127) * 8 + e] = acc[e];
      }
      const uint32_t tag = ld_relaxed(&g_epoch) % 3 + 1;
      bar_sync(1, 256);
      if (tid < 128) {
        uint32_t o[8];
#pragma unroll
        for (int e = 0; e < 8; e++) o[e] = __float_as_uint(rbf(acc[e] + red[tid * 8 + e])) | tag;
        st_relaxed4(g_mod + col, o[0], o[1], o[2], o[3]);
        st_relaxed4(g_mod + col + 4, o[4], o[5], o[6], o[7]);
        const uint4 wr = ldg_nc4(P.w_r + tid * 8);
        const uint32_t wv[4] = {wr.x, wr.y, wr.z, wr.w};
        float dsum = 0.f;
#pragma unroll
        for (int e = 0; e < 8; e++) {
          const float m = bf_hi(o[e]);
          dsum += (b == NMAIN + 2 ? rbf(1.f + m) : m) * ((e & 1) ? bf_hi(wv[e >> 1]) : bf_lo(wv[e >> 1]));
        }
#pragma unroll
        for (int k = 16; k > 0; k >>= 1) dsum += __shfl_xor_sync(0xffffffffu, dsum, k);
        if (lane == 0) st_relaxed(g_mod + (b - NMAIN) * 4 + warp, tagf(dsum, tag));
      }
    }
    PROF(2, tid == 0, 1);
    return;
  }

  const int rank = b & 1;
  const int rb = ((b >> 4) << 1) | rank, cj = (b >> 1) & 7;
  const bool late = b & 4;
  const uint32_t bfull = base + OFF_BAR, bempty = bfull + NSLOT * 8;
  const uint32_t gfull = bempty + NSLOT * 8, gempty = gfull + 32;
  const uint32_t bar_ofull = gempty + 32;
  const uint32_t bar_ofree = bar_ofull + 32;
  const uint32_t bar_par = bar_ofree + 32;
  const uint32_t bar_mod = bar_par + 8;
  const uint32_t bar_pread = bar_mod + 8;
  const uint32_t bar_xres = bar_pread + 8;
  const uint32_t bar_ring = bar_xres + 8;
  const uint32_t bar_box = bar_ring + 24;
  const uint32_t bar_go = bar_box + 96;
  const uint32_t bar_go2 = bar_go + 16;
  const uint32_t bar_cnt = bar_go + 24;
  const uint32_t xfull = bar_go + 40, xempty = xfull + 32;
  const uint32_t bar_hw = xempty + 32, bar_hx = bar_hw + 8;
  const uint32_t bar_hpub = bar_hx + 16;
  const uint32_t bar_win = bar_hpub + 16;
  const uint32_t bar_rx = bar_win + 8;
  const uint32_t bar_sel = bar_rx + 8;
  const uint32_t bar_gate = bar_sel + 8;
  const uint32_t bar_rel = bar_gate + 8;
  const uint32_t bar_od = bar_rel + 8;
  const uint32_t bar_mod2 = bar_od + 8;
  const uint32_t bar_res = bar_go + 8;
  const uint32_t stage = base + OFF_STAGE, par = base + OFF_PAR;

  if (warp == 10 && elect_one()) prefetch_map(&maps.wm);
  if (warp == 8 && elect_one()) {
    for (int s = 0; s < NSLOT; s++) { mbar_init(bfull + s * 8, 1); mbar_init(bempty + s * 8, 16); }
    for (int s = 0; s < 4; s++) { mbar_init(gfull + s * 8, 1); mbar_init(gempty + s * 8, 16); mbar_init(xfull + s * 8, 1); mbar_init(xempty + s * 8, 8); mbar_init(bar_ofree + s * 8, 1); mbar_init(bar_ofull + s * 8, 128); }
    mbar_init(bar_par, 64); mbar_init(bar_mod, 256); mbar_init(bar_pread, 2); mbar_init(bar_xres, 1);
    mbar_init(bar_ring, 8); mbar_init(bar_ring + 8, 8); mbar_init(bar_ring + 16, 8);
    mbar_init(bar_go, 1); mbar_init(bar_go2, 1); mbar_init(bar_cnt, 1); mbar_init(bar_cnt + 8, 1); mbar_init(bar_hpub, 8); mbar_init(bar_hpub + 8, 8); mbar_init(bar_res, 1); mbar_init(bar_win, 1); mbar_init(bar_rx, 1); mbar_init(bar_sel, 64); mbar_init(bar_gate, 8); mbar_init(bar_rel, 8); mbar_init(bar_od, 1); mbar_init(bar_mod2, 64);
    for (int s = 0; s < 12; s++) mbar_init(bar_box + s * 8, 1);
    asm volatile("fence.mbarrier_init.release.cluster;" ::: "memory");
    prefetch_map(&maps.x); prefetch_map(&maps.wq); prefetch_map(&maps.k); prefetch_map(&maps.v);
  }
  if (warp == 9 && elect_one()) {
    mbar_init(bar_hw, 1); mbar_init(bar_hx, 1); mbar_init(bar_hx + 8, 1);
    asm volatile("fence.mbarrier_init.release.cluster;" ::: "memory");
    mbar_expect_tx(bar_hw, 32768);
    mbar_expect_tx(bar_hx, 16384);
    mbar_expect_tx(bar_hx + 8, 16384);
    const __nv_bfloat16* xs = P.x + (size_t)(rb * 128 + cj * 16) * DM;
    bulk_load(base + 2 * GST_BYTES, xs, 16384, bar_hx);
    if (!late) {
      tma2d(stage, &maps.wm, (b >> 1) * 32, rank * 512, bar_hw);
      tma2d(stage + 16384, &maps.wm, (b >> 1) * 32, rank * 512 + 256, bar_hw);
    }
    bulk_load(base + 3 * GST_BYTES, xs + 8 * DM, 16384, bar_hx + 8);
  }
  cluster_arrive();

  if (warp >= 8) {
    asm volatile("setmaxnreg.dec.sync.aligned.u32 40;");
    if (warp < 10) bar_arrive(1, 320);
    const uint32_t epoch = ld_relaxed(&g_epoch);
    cluster_wait();
    if (warp == 8) {
      const int kvrow = (cj >> 1) * SK + (SK - WIN);
      int wch = cj * 8 + rank * 2;
#pragma unroll 1
      for (int ps = 0; ps < 3; ps++) {
        const CUtensorMap* mw = ps == 2 ? &maps.wo : &maps.wq;
        const uint32_t xt = ps == 1 ? XT1 : XT2, wt = ps == 0 ? WT0 : (ps == 1 ? WT1 : WT2);
        const int nst = ps == 2 ? 32 : 16;
#pragma unroll 1
        for (int i = 0; i < nst; i++) {
          const uint32_t bf = gfull + (i & 3) * 8;
          const int kt = ps == 2 ? (((cj & 1) * 4 + ((i >> 1) & 3)) * 4 + (i >> 3)) * 2 + (i & 1) : (ps ? i : slice_of(i) + (b & 14)) & 15;
          const uint32_t wd = base + unit_of(wt, i & 3) + rank * UNIT, xd = base + unit_of(xt, i & 3);
          const uint8_t* xs = g_act + (uint32_t)(rb * 80 + (ps - 1) * 16 + kt) * UNIT;
          if (ps == 0 && i == HD) mbar_wait(bar_mod, 0);
          if (ps == 2 && (i & 7) == 0 && i != 8) mbar_wait(i ? bar_cnt + i - 16 : bar_ofree + 24, 0);
          if ((i & 7) == 0) fence_async();
          if (i == RES0) mbar_wait(bar_res, 0);
          mbar_wait(bf, ((i >> 2) & 1) ^ 1);
          if (elect_one()) {
            mbar_expect_tx(bf, ps ? GST_BYTES : 2 * UNIT);
            if (ps && i < 2) bulk_load_stream(xd, xs, UNIT, bf);
            mbar_arrive_pred(bar_go, i == GOST);
            mbar_arrive_pred(bar_go2, ps == 1 && i == PG0);
            mbar_arrive_pred(bar_od, ps && i == (ps == 1 ? ODS1 : ODS) + 1);
            if (i == RES0) mbar_expect_tx(bar_xres, 32768);
          }
          const int wk = (i == 31 ? kt ^ (rank * 32) : kt) * 64, wc = i == 31 ? cj * 2 : wch;
          const uint64_t xp = i == 31 ? l2_normal() : l2_stream();
          mbar_wait(ps && i < 4 ? bempty + i * 8 : gempty + (i & 3) * 8, ((i >> 2) & 1) ^ 1);
          if (elect_one()) {
            tma3d_mc<true>(wd, mw, 0, wk, wc, bf);
            if (ps && i > 2) bulk_load_stream(xd, xs, UNIT, bf, xp);
            if (i == RES0 || i == RES1) tma2d(base + OFF_RES + (i == RES1) * UNIT, &maps.x, cj * 128 + (i == RES1) * 64, rb * 128, bar_xres);
          }
          if (ps && i == 2) {
            mbar_wait(bar_ofree + (ps - 1) * 16, 0);
            if (elect_one()) bulk_load_stream(xd, xs, UNIT, bf);
          }
        }
        if (ps == 2) break;
        wch = ps ? ((wch >> 3) ^ rank) * 2 : wch + 4;
#pragma unroll 1
        for (int u = 0; u < 16; u++) {
          const bool isk = (u == 0) || ((u & 1) && u < 15), kept = (0x1680 >> u) & 1;
          const int blk = (0x472FAD84u >> (u * 2)) & 3;
          const uint32_t sl = base + unit_of(ps ? AT1 : AT0, u & 3) + rank * UNIT, bf = bfull + (u & 3) * 8;
          mbar_wait(bf, ((u >> 2) & 1) ^ 1);
          if (!kept && elect_one()) mbar_expect_tx(bf, SLOT_BYTES);
          mbar_wait(u < 4 ? gempty + ((u + 1) >> 1) * 8 : bempty + (u & 3) * 8, ((u >> 2) & 1) ^ 1);
          if (elect_one()) {
            if (kept) mbar_arrive(bf);
            else if (ps && (blk >= 2 || u > 8)) tma3d_mc<true>(sl, isk ? &maps.k : &maps.v, 0, kvrow + blk * 128, rank, bf);
            else tma3d_mc<false>(sl, isk ? &maps.k : &maps.v, 0, kvrow + blk * 128, rank, bf);
          }
        }
      }
      if (elect_one()) mbar_expect_tx(bar_rx, UNIT);
      mbar_wait(bar_rel, 0);
      if (elect_one()) {
        bulk_load_stream(base + UNIT, g_act + (uint32_t)(rb * 80 + 16 + 63 - (cj & 1) * 32) * UNIT, UNIT, bar_rx);
      }
      if (b < NFFN) {
#pragma unroll 1
        for (int u = 0; u < 12; u++) {
          const uint32_t dst = base + unit_of(u < 4 ? FT_G : (u < 8 ? FT_U : FT_D), u & 3);
          if (elect_one()) mbar_expect_tx(bar_box + u * 8, UNIT);
          if (u == 0 || u == 2 || u == 8) mbar_wait(bar_ring + (u == 8 ? 16 : u * 4), 0);
          const int fp = u < 8 ? FPACE0 : FPACE;
          if (u >= fp) mbar_wait(bar_box + (u - fp) * 8, 0);
          if (elect_one()) {
            if (u < 8) tma2d(dst, u < 4 ? &maps.wg : &maps.wu, b * 32, (u & 3) * 256, bar_box + u * 8);
            else tma3d(dst, &maps.wd, 0, b * 32, (u - 8) * 4, bar_box + u * 8);
          }
        }
      }
    } else if (warp == 9) {
      const uint32_t target = 8 * (epoch + 1);
      uint32_t hmask = 0;
#pragma unroll 1
      for (int i = 0; i < 16; i++) {
        if (i == HDX) mbar_wait(bar_mod, 0);
        const int kt = (2 * cj + slice_of(i)) & 15;
        const uint32_t need = i == 15 ? 0xffffu : 1u << kt;
        if (i >= NRS && (hmask & need) != need) {
          uint32_t n = 0;
          do { hmask = __ballot_sync(0xffffffffu, ld_acquire(&g_cnt_h[rb * 32 + (lane & 15)]) == epoch + 1); watchdog(n); } while ((hmask & need) != need);
          PROF(1, lane == 0 && i == NRS, 26);
          fence_async();
        }
        mbar_wait(xempty + (i & 3) * 8, ((i >> 2) & 1) ^ 1);
        if (elect_one()) {
          mbar_expect_tx(xfull + (i & 3) * 8, UNIT);
          if (i < NRS) tma2d(base + (i & 3) * GST_BYTES, &maps.x, kt * 64, rb * 128, xfull + (i & 3) * 8);
          else bulk_load_stream(base + (i & 3) * GST_BYTES, g_act + (uint32_t)(rb * 80 + kt) * UNIT, UNIT, xfull + (i & 3) * 8);
        }
      }
      prefetch_map(&maps.wo);
#pragma unroll 1
      for (int t = 0; t < 4; t++) {
        if (t & 1) mbar_wait(bar_od, t >> 1);
        const int ops = OPS >> (t & 1);
#pragma unroll 1
        for (int p = 0; p < 32768; p += ops) {
          const uint32_t w = p >> 14, c = (p >> 13) & 1, off = w * 8192 + (p & 8191);
          mbar_wait(bar_ofull + (t & 1) * 16 + w * 8, t >> 1);
          if (elect_one()) {
            bulk_store(g_act + (uint32_t)(rb * 80 + 16 + (cj * 4 + t) * 2 + c) * UNIT + off, base + unit_of(QT, 2 * t + c) + off, ops);
            asm volatile("cp.async.bulk.commit_group;" ::: "memory");
            asm volatile("cp.async.bulk.wait_group.read 0;" ::: "memory");
          }
        }
        if (elect_one()) {
          mbar_arrive(t < 3 ? bar_ofree + t * 8 : bar_res);
          asm volatile("cp.async.bulk.wait_group 0;" ::: "memory");
          fence_async();
          red_release(&g_cnt_o[((rb * 4 + t) * 2 + (cj >> 2)) * 32], 2);
        }
        if (t) {
          wait_counter(&g_cnt_o[(rb * 8 + 2 * t + (cj & 1)) * 32], target);
          if (t & 1) wait_counter(&g_cnt_o[(rb * 8 + (t == 1 ? cj & 1 : 7 - (cj & 1))) * 32], target);
          if (elect_one()) mbar_arrive(t == 1 ? bar_ofree + 24 : bar_cnt + t * 8 - 16);
        }
      }
      PROF(2, lane == 0, 27);
      const uint32_t tag = epoch % 3 + 1;
      const uint32_t* inbox = g_cand + (b >> 4) % CR * 512 + (lane & 15) * CS;
      mbar_wait(bar_ring + 16, 0);
      uint32_t c0 = ld_relaxed(inbox), n = 0;
#define CAND_STEP(cv)                                                                                        \
      {                                                                                                      \
        const bool valid = (cv & 3u) == tag, all = __all_sync(0xffffffffu, valid);                           \
        const uint32_t best = __reduce_max_sync(0xffffffffu, valid ? cv : 0u);                               \
        const uint32_t blk = __ffs(__ballot_sync(0xffffffffu, cv == best)) - 1;                              \
        if (best) sts2(par + PAR_CONST + 56, best, (blk << 7 | (~best >> 2 & 127)) | (all ? 0x1800 : 0x800)); \
        if (all) break;                                                                                      \
        cv = ld_relaxed(inbox);                                                                              \
      }
      while (true) { CAND_STEP(c0) watchdog(n); }
    } else {
      const int t2 = tid - 320;
      if (late && warp == 10) {
        mbar_wait(bar_hx, 0);
        if (elect_one()) {
          tma2d(stage, &maps.wm, (b >> 1) * 32, rank * 512, bar_hw);
          tma2d(stage + 16384, &maps.wm, (b >> 1) * 32, rank * 512 + 256, bar_hw);
        }
      }
      {
        const uint32_t tag = epoch % 3 + 1;
        mbar_wait(bar_hx + 8, 0);
        mbar_wait(bar_hw, 0);
        __nanosleep(late ? OSL2 : OSL);
        {
          const uint32_t t7 = (warp & 1) * 64 + (lane >> 4) * 32 + 16 + (lane & 15);
          const uint32_t* pm = g_modp + ((cj * 128 + t7 * 4) & (DM - 1));
          uint4 m0, m1, m2, m3;
          uint32_t n = 0;
          do {
            m0 = ld_relaxed4(pm); m1 = ld_relaxed4(pm + 2 * DM); m2 = ld_relaxed4(pm + DM); m3 = ld_relaxed4(pm + 3 * DM);
            watchdog(n);
          } while (!__all_sync(0xffffffffu, tag_ok(m0, tag) && tag_ok(m1, tag) && tag_ok(m2, tag) && tag_ok(m3, tag)));
          write_table(par, false, t7, m0, m1);
          write_table(par, true, t7, m2, m3);
          mbar_arrive(bar_mod2);
        }
      }
      mbar_wait(bar_hpub + (warp & 1) * 8, 0);
      PROF(1, t2 == 0, 24);
#pragma unroll 1
      for (int c = 0; c < 8; c++) {
        const uint32_t off = (warp & 1) * UNIT + c * 2048 + lane * 16;
        uint8_t* dst = g_act + (uint32_t)(rb * 80 + cj * 2) * UNIT + off;
        const uint4 v0 = lds4(stage + off), v1 = lds4(stage + off + 512), v2 = lds4(stage + off + 1024), v3 = lds4(stage + off + 1536);
        stg4(dst, v0); stg4(dst + 512, v1); stg4(dst + 1024, v2); stg4(dst + 1536, v3);
      }
      __syncwarp();
      PROF(1, t2 == 0, 15);
      if (lane == 0) {
        mbar_arrive(bar_pread);
        red_release(&g_cnt_h[rb * 32 + cj * 2 + (warp & 1)], 1);
        PROF(1, t2 == 0, 25);
        prefetch_map(&maps.wg); prefetch_map(&maps.wu); prefetch_map(&maps.wd); prefetch_map(&maps.out);
      }
      __syncwarp();
      if (b < NFFN) {
        mbar_wait(bar_go2, 0);
        const __nv_bfloat16* pg = ((b & 1) ? P.w_up : P.w_gate) + (b >> 1) * 64 + (size_t)t2 * FF;
        const __nv_bfloat16* pd = P.w_down + (size_t)b * 32768 + t2 * 64;
        PROF(2, t2 == 0, 13);
#pragma unroll 1
        for (int i = 0; i < WN; i += WB) {
          uint32_t v[WB];
#pragma unroll
          for (int u = 0; u < WB; u++) {
            const int k = i + u;
            asm volatile("ld.global.cg.L2::128B.u32 %0, [%1];" : "=r"(v[u]) : "l"(k < 16 ? pg + (size_t)k * 64 * FF : pd + (k - 16) * 4096));
          }
#pragma unroll
          for (int u = 1; u < WB; u++) v[0] ^= v[u];
          sts1(par + PAR_SINK + t2 * 4, v[0]);
        }
        PROF(2, t2 == 0, 14);
      }
      const uint32_t tag = epoch % 3 + 1;
      mbar_wait(bar_go, 0);
      bar_sync(4, 64);
      if (warp == 10) {
        const uint32_t* src = g_mod + 2 * DM + cj * 128 + lane * 4;
        const uint2 wr = *reinterpret_cast<const uint2*>(P.w_r + cj * 128 + lane * 4);
        uint4 vga, vsb, vcb, vgb;
        uint32_t n = 0;
        do {
          vga = ld_relaxed4(src); vsb = ld_relaxed4(src + DM); vcb = ld_relaxed4(src + 2 * DM); vgb = ld_relaxed4(src + 3 * DM);
          watchdog(n);
        } while (!__all_sync(0xffffffffu, tag_ok(vga, tag) && tag_ok(vsb, tag) && tag_ok(vcb, tag) && tag_ok(vgb, tag)));
        const float c0 = rbf(1.f + bf_hi(vcb.x)), c1 = rbf(1.f + bf_hi(vcb.y)), c2 = rbf(1.f + bf_hi(vcb.z)), c3 = rbf(1.f + bf_hi(vcb.w));
        const float a0 = c0 * bf_lo(wr.x), a1 = c1 * bf_hi(wr.x), a2 = c2 * bf_lo(wr.y), a3 = c3 * bf_hi(wr.y);
        const uint32_t h0 = pack_bf(a0, a1), h1 = pack_bf(a2, a3);
        const uint32_t t1 = par + PAR_T1 + (lane >> 2) * 64 + (lane & 1) * 32 + (lane & 2) * 2;
        sts1(t1, h0); sts1(t1 + 8, pack_bf(a0 - bf_lo(h0), a1 - bf_hi(h0)));
        sts1(t1 + 16, h1); sts1(t1 + 24, pack_bf(a2 - bf_lo(h1), a3 - bf_hi(h1)));
        const uint32_t tg = par + PAR_SINK + (lane >> 3) * 64 + (lane & 1) * 32 + (lane & 6) * 2;
        sts1(tg, __byte_perm(vga.x, vga.y, 0x7632)); sts1(tg + 16, __byte_perm(vga.z, vga.w, 0x7632));
        sts4(par + PAR_T2 + lane * 32, make_uint4(pack_bf(c0, c1), __byte_perm(vsb.x, vsb.y, 0x7632), __byte_perm(vgb.x, vgb.y, 0x7632), __byte_perm(vga.x, vga.y, 0x7632)));
        sts4(par + PAR_T2 + lane * 32 + 16, make_uint4(pack_bf(c2, c3), __byte_perm(vsb.z, vsb.w, 0x7632), __byte_perm(vgb.z, vgb.w, 0x7632), __byte_perm(vga.z, vga.w, 0x7632)));
      } else {
        const uint4 g = poll4((lane & 8) ? g_mod + 8 - (lane & 1) * 4 : g_mod + 5 * DM + (b >> 4) * 128 + (lane & 7) * 16 + (b & 12), tag);
        sts1(par + PAR_CONST + 60, 0);
        if (lane < 8) sts1(par + PAR_CONST + 16 + lane * 4, (b & 2) ? ((b & 1) ? g.w : g.z) : ((b & 1) ? g.y : g.x));
        else if (lane < 10) sts2(par + PAR_CONST + (lane - 8) * 8, __float_as_uint(untag_sum(g.x, g.y) + untag_sum(g.z, g.w)), epoch);
      }
      __syncwarp();
#pragma unroll 1
      for (int q = 0; q < 32; q++) {
        st_b128(g_xch + ((size_t)b * 8 * 256 + q * 64 + t2) * 4, (epoch & 1) << 16, 0, 0, 0);
        __nanosleep(RSL);
      }
      for (int q = 0; q < 2; q++) st_relaxed4(g_stats + (((rb * 8 + q * 4 + (t2 >> 4)) * 8 + cj) * 16 + (t2 & 15)) * 4, 0, 0, 0, 0);
      if (b < NFFN)
        for (int q = 0; q < 2; q++) st_relaxed4(ypart_slot(b, q * 64 + t2), 0, 0, 0, 0);
      st_relaxed4(g_row + rb * 2 * DM + (t2 >> 5) * DM + cj * 128 + (t2 & 31) * 4, 0, 0, 0, 0);
      __threadfence();
      mbar_arrive(bar_par);
      mbar_wait(bar_gate, 0);
      uint32_t have = 0, n = 0;
      while (true) {
        const uint32_t st = lds1(par + PAR_CONST + 60) >> 7;
        if ((st & 31) != have) {
          const uint32_t* hsrc = g_row + (st & 15) * 2 * DM + t2 * 4;
          uint4 hv[4];
          bool ok = true;
#pragma unroll
          for (int i = 0; i < 4; i++) hv[i] = ld_pairs(hsrc + i * 256);
#pragma unroll
          for (int i = 0; i < 4; i++) {
            sts2(base + ((FT_G >> i * 4) & 15) * UNIT + (warp & 1) * 8192 + 256 + lane * 8, hv[i].x, hv[i].z);
            ok = ok && hv[i].y == tag && hv[i].w == tag;
          }
          have = __all_sync(0xffffffffu, ok) ? st & 31 : 0;
        }
        if ((st ^ have) == 32) break;
        watchdog(n);
      }
      mbar_arrive(bar_sel);
    }
    __syncwarp();
    cluster_arrive();
    {
      const uint32_t tag = epoch % 3 + 1, t3 = tid - 256;
      mbar_wait(bar_win, 0);
      uint2 win = lds2(par + PAR_CONST + 56);
      win.y &= 0x7ff;
      const uint32_t* fsrc = g_row + (win.y >> 7) * 2 * DM + (b >> 4) * 128 + (t3 & 7) * 16 + (b & 6) * 2 + ((b >> 2) & 2);
      const uint32_t* ysrc = ypart_slot(min(t3, NFFN - 1), b);
      uint2 fh = ld_pair(fsrc), fx = ld_pair(fsrc + DM);
      uint4 ya = ld_b128(ysrc);
      const float rwin = __uint_as_float(((int)win.x < 0 ? win.x & 0x7fffffffu : ~win.x) & ~0x1ffu);
      const float rs = rbf(rcp(1.f + __expf(-rbf(rwin))));
      uint32_t n = 0;
      while (__any_sync(0xffffffffu, fh.y != tag || fx.y != tag)) { fh = ld_pair(fsrc); fx = ld_pair(fsrc + DM); watchdog(n); }
      while (true) {
        const bool miss = ((ya.x & 1) | (ya.y & 1) << 1) != tag;
        if (!__any_sync(0xffffffffu, miss)) break;
        if (miss) ya = ld_b128(ysrc);
        watchdog(n);
      }
      PROF(8, t3 == 0, 5);
      float y[8] = {bf_lo(ya.x & ~1u), bf_hi(ya.x), bf_lo(ya.y & ~1u), bf_hi(ya.y), bf_lo(ya.z), bf_hi(ya.z), bf_lo(ya.w), bf_hi(ya.w)};
#pragma unroll
      for (int h = 4; h > 0; h >>= 1) {
        const bool up = lane & (h * 2);
#pragma unroll
        for (int e = 0; e < h; e++) y[e] = (up ? y[e + h] : y[e]) + __shfl_xor_sync(0xffffffffu, up ? y[e] : y[e + h], h * 2);
      }
      y[0] += __shfl_xor_sync(0xffffffffu, y[0], 1);
      if (!(lane & 1)) sts1(par + PAR_RED + 64 + t3 * 2, __float_as_uint(y[0]));
      bar_sync(4, 128);
      if (t3 < 8) {
        float y0 = 0.f;
#pragma unroll
        for (int w7 = 0; w7 < 7; w7++) y0 += __uint_as_float(lds1(par + PAR_RED + 64 + w7 * 32 + t3 * 4));
        const uint32_t gv = lds1(par + PAR_CONST + 16 + t3 * 4);
        const uint32_t upd = hmul2(pack_bf(y0, y0), pack_bf(rs, rs));
        const uint32_t r = hadd2(fx.x, hmul2(__byte_perm(gv, gv, 0x3232), hadd2(fh.x, upd)));
        reinterpret_cast<uint16_t*>(P.out)[(size_t)win.y * DM + (b >> 4) * 128 + t3 * 16 + (b & 15)] = (b & 1) ? r >> 16 : r;
        if (b == 0 && t3 == 0) st_relaxed(&g_epoch, epoch + 1);
      }
      PROF(31, t3 == 0, 36);
    }
    cluster_wait();
  } else {
    const int wg = warp >> 2;

    uint32_t tag;
    {
      uint32_t* const pmod = g_modp + rank * 2 * DM + (b >> 1) * 32 + lane;
      uint32_t* const pln = g_ln1 + (rb * 128 + cj * 16 + warp) * 4;
      uint32_t sc[8];
      if (C1) {
        sc[0] = ldg_nc1(P.c + rank * 512 + tid * 2);
      } else {
#pragma unroll
        for (int k = 0; k < 8; k++) sc[k] = ldg_nc1(P.c + rank * 512 + warp * 64 + k * 8 + (lane & 3) * 2);
      }
      const uint32_t epoch = ld_relaxed(&g_epoch);
      if (warp == 0) st_relaxed(pmod, 0);
      if (lane == 0) { st_b128(pln, 0, 0, 0, 0); st_b128(pln + 32, 0, 0, 0, 0); }
      asm volatile("setmaxnreg.inc.sync.aligned.u32 232;");
      bar_sync(1, 320);
      if (C1) {
        const uint32_t v = pack_bf(silu_f(bf_lo(sc[0])), silu_f(bf_hi(sc[0])));
#pragma unroll
        for (int k = 0; k < 8; k++) sc[k] = __shfl_sync(0xffffffffu, v, k * 4 + (lane & 3));
      } else {
#pragma unroll
        for (int k = 0; k < 8; k++) sc[k] = pack_bf(silu_f(bf_lo(sc[k])), silu_f(bf_hi(sc[k])));
      }
      keep(sc);
      tag = epoch % 3 + 1;
#pragma unroll
      for (int part = 0; part < 4; part++) {
        if (!(part & 1)) {
          const uint32_t xa = base + (2 + part / 2) * GST_BYTES + warp * 2048 + lane * 16;
          mbar_wait(bar_hx + part * 4, 0);
          float s0 = 0.f, s1 = 0.f, q0 = 0.f, q1 = 0.f;
#pragma unroll
          for (int q = 0; q < 4; q++) {
            const uint4 xv = lds4(xa + q * 512);
            const uint32_t u[4] = {xv.x, xv.y, xv.z, xv.w};
#pragma unroll
            for (int e = 0; e < 4; e++) { const float lo = bf_lo(u[e]), hi = bf_hi(u[e]); s0 += lo; s1 += hi; q0 += lo * lo; q1 += hi * hi; }
          }
          s0 += s1; q0 += q1;
#pragma unroll
          for (int o = 16; o > 0; o >>= 1) { s0 += __shfl_xor_sync(0xffffffffu, s0, o); q0 += __shfl_xor_sync(0xffffffffu, q0, o); }
          const float mean = s0 * (1.f / DM);
          float mb, sd;
          ln_scalars(mean, fmaxf(q0 * (1.f / DM) - mean * mean, 0.f), mb, sd);
          uint32_t ih, il;
          split_inv(sd, ih, il);
          if (lane == 0) st_b128(pln + part * 16, pack_bf(mb, mb), ih, il, tag);
          PROF(1, tid == 0 && part == 2, 4);
        } else if (late == (part == 3)) {
          const uint32_t fr = (lane & 7) + (lane >> 4) * 8, tq = lane & 3;
          const uint32_t wa = stage + warp * 4096 + fr * 64 + ((((lane >> 3) & 1) ^ ((fr >> 1) & 3)) << 4);
          float d0[4] = {0.f, 0.f, 0.f, 0.f}, d1[4] = {0.f, 0.f, 0.f, 0.f};
          mbar_wait(bar_hw, 0);
#pragma unroll
          for (int ks = 0; ks < 4; ks++) {
            uint32_t w[8];
            ldmatrix4t(wa + ks * 1024, w[0], w[1], w[2], w[3]);
            ldmatrix4t((wa ^ 32) + ks * 1024, w[4], w[5], w[6], w[7]);
            mma16816(d0, w[0], w[1], w[2], w[3], sc[2 * ks], sc[2 * ks + 1]);
            mma16816(d1, w[4], w[5], w[6], w[7], sc[2 * ks], sc[2 * ks + 1]);
          }
          sts1(base + 2 * GST_BYTES + warp * 2048 + (tq * 8 + (lane >> 2)) * 4, __float_as_uint((tq & 2) ? ((tq & 1) ? d1[2] : d1[0]) : ((tq & 1) ? d0[2] : d0[0])));
          bar_sync(1, 256);
          if (warp == 0) {
            float s = 0.f;
#pragma unroll
            for (int w8 = 0; w8 < 8; w8++) s += __uint_as_float(lds1(base + 2 * GST_BYTES + w8 * 2048 + lane * 4));
            st_relaxed(pmod, (__float_as_uint(s) & ~3u) | tag);
          }
          PROF(1, tid == 0, 3);
        }
      }
      cluster_wait();
      if (wg == 1) bar_arrive(2, 256);
    }

    const uint32_t rempty = lane < 2 ? mapa(bempty, lane & 1) : 0;
    constexpr uint32_t GE = NSLOT * 8 + 32;
    float o[64], s[64];
#pragma unroll 1
    for (int ps = 0; ps < 3; ps++) {
      {
        const uint32_t xt = ps == 1 ? XT1 : XT2, wt = ps == 1 ? WT1 : WT2;
        const int nst = ps == 2 ? 28 : 14;
        if (ps == 0) {
          float ga[64], gb[64];
#pragma unroll
          for (int i = 0; i < 64; i++) { ga[i] = 0.f; gb[i] = 0.f; }
          uint32_t a[2][16];
          const uint32_t l = fresh_lane();
          uint32_t fa[4];
#pragma unroll
          for (int kk = 0; kk < 4; kk++) fa[kk] = (base + wg * 8192 + frag_offset(warp)) ^ (kk * 32);
          const uint32_t mt = par + (l & 3) * 16;
          auto fetch = [&](int i, uint32_t (&f)[16], uint32_t z) {
            mbar_wait(xfull + (i & 3) * 8, i >> 2);
#pragma unroll
            for (int kk = 0; kk < 4; kk++) ldmatrix4(fa[kk] + (i & 3) * GST_BYTES + z, f[4 * kk], f[4 * kk + 1], f[4 * kk + 2], f[4 * kk + 3]);
          };
          const bool oddw = warp & 2;
          uint4 r0, r1;
          {
            const uint32_t t7 = (warp & 1) * 64 + (l >> 4) * 32 + (l & 15);
            const uint32_t* pm = g_modp + wg * DM + ((cj * 128 + t7 * 4) & (DM - 1));
            const uint32_t* pr = g_ln1 + (rb * 128 + warp * 16 + (l >> 2)) * 4;
            uint4 m0 = make_uint4(tag, tag, tag, tag), m1 = m0;
            if (!oddw) { m0 = ld_relaxed4(pm); m1 = ld_relaxed4(pm + 2 * DM); }
            r0 = ld_b128(pr); r1 = ld_b128(pr + 32);
            fetch(0, a[0], 0); fetch(1, a[1], 0);
            uint32_t n = 0;
            bool written = false;
#pragma unroll 1
            while (true) {
              uint32_t miss;
              asm volatile("{ .reg .pred p0, p1, p2, p3; .reg .b32 t, u;\n"
                           "lop3.b32 t, %1, %2, %19, 0x7e; lop3.b32 u, %3, %4, %19, 0x7e; or.b32 t, t, u; and.b32 t, t, 3; setp.ne.u32 p0, t, 0;\n"
                           "lop3.b32 t, %5, %6, %19, 0x7e; lop3.b32 u, %7, %8, %19, 0x7e; or.b32 t, t, u; and.b32 t, t, 3; setp.ne.u32 p1, t, 0;\n"
                           "setp.ne.u32 p2, %12, %19; setp.ne.u32 p3, %16, %19;\n"
                           "@p0 ld.relaxed.gpu.global.v4.u32 {%1, %2, %3, %4}, [%17];\n"
                           "@p1 ld.relaxed.gpu.global.v4.u32 {%5, %6, %7, %8}, [%17 + 8192];\n"
                           "@p2 ld.relaxed.gpu.global.v4.u32 {%9, %10, %11, %12}, [%18];\n"
                           "@p3 ld.relaxed.gpu.global.v4.u32 {%13, %14, %15, %16}, [%18 + 128];\n"
                           "or.pred p0, p0, p1; or.pred p2, p2, p3; vote.sync.any.pred p0, p0, 0xffffffff; vote.sync.any.pred p2, p2, 0xffffffff;\n"
                           "selp.u32 t, 1, 0, p0; selp.u32 u, 2, 0, p2; or.b32 %0, t, u; }"
                           : "=r"(miss), "+r"(m0.x), "+r"(m0.y), "+r"(m0.z), "+r"(m0.w), "+r"(m1.x), "+r"(m1.y), "+r"(m1.z), "+r"(m1.w),
                             "+r"(r0.x), "+r"(r0.y), "+r"(r0.z), "+r"(r0.w), "+r"(r1.x), "+r"(r1.y), "+r"(r1.z), "+r"(r1.w)
                           : "l"(pm), "l"(pr), "r"(tag) : "memory");
              if (!(miss & 1) && !written) {
                written = true;
                if (!oddw) write_table(par, wg, t7, m0, m1);
                mbar_arrive(bar_mod);
              }
              if (!miss) break;
              watchdog(n);
            }
          }
          const uint32_t zero = r0.w ^ tag;
          auto normalize = [&](uint32_t (&f)[16]) {
#pragma unroll
            for (int k = 0; k < 16; k += 2) { f[k] = ln_norm(f[k], r0.x, r0.y, r0.z); f[k + 1] = ln_norm(f[k + 1], r1.x, r1.y, r1.z); }
          };
          auto modulate = [&](int i, uint32_t (&f)[16]) {
#pragma unroll
            for (int kk = 0; kk < 4; kk++) {
              const uint4 m = lds4(mt + slice_of(i) * 256 + kk * 64);
              f[4 * kk] = hfma2(f[4 * kk], m.x, m.z); f[4 * kk + 1] = hfma2(f[4 * kk + 1], m.x, m.z);
              f[4 * kk + 2] = hfma2(f[4 * kk + 2], m.y, m.w); f[4 * kk + 3] = hfma2(f[4 * kk + 3], m.y, m.w);
            }
            keep(f);
            mbar_arrive_pred(xempty + (i & 3) * 8, l == 0);
          };
          auto publish = [&](int u, uint32_t (&f)[16]) {
#pragma unroll
            for (int kk = 0; kk < 4; kk++) stmatrix4(fa[kk] + OFF_STAGE + u * UNIT, f[4 * kk], f[4 * kk + 1], f[4 * kk + 2], f[4 * kk + 3]);
            __syncwarp();
            mbar_arrive_pred(bar_hpub + u * 8, l == 0);
          };
          auto multiply = [&](int i, uint32_t (&f)[16]) {
            mbar_wait(gfull + (i & 3) * 8, i >> 2);
            const uint64_t db = make_desc(base + (i & 3) * GST_BYTES + UNIT, 8192, 1024);
            wg_fence();
#pragma unroll
            for (int kk = 0; kk < 4; kk++) mma256_rs(ga, gb, f[4 * kk], f[4 * kk + 1], f[4 * kk + 2], f[4 * kk + 3], db + kk * 128);
            wg_commit();
          };
          auto next = [&](int i, uint32_t (&f)[16]) {
            wg_wait<1>();
            mbar_arrive_cl(rempty, GE + ((i + 2) & 3) * 8);
            uint32_t z = zero;
#pragma unroll
            for (int k = 0; k < 16; k += 2) asm volatile("lop3.b32 %0, %1, %2, %0, 0xA8;" : "+r"(z) : "r"(f[k]), "r"(f[k + 1]));
            fetch(i, f, z);
            normalize(f);
            if (i == 2) { keep(f); mbar_wait(bar_mod2, 0); }
            modulate(i, f); multiply(i, f);
          };
          normalize(a[0]);
          if (!N1L) normalize(a[1]);
          keep(a[0]); keep(a[1]);
          mbar_wait(bar_mod, 0);
          PROF(1, tid == 0, 2);
          modulate(0, a[0]); multiply(0, a[0]); publish(0, a[0]);
          if (N1L) { keep(a[1]); normalize(a[1]); }
          modulate(1, a[1]); multiply(1, a[1]);
#pragma unroll 1
          for (int i = 2; i < NRS; i += 2) {
            next(i, a[0]);
            if (i == 2) publish(1, a[0]);
            next(i + 1, a[1]);
          }
          wg_wait<1>();
          mbar_arrive_cl(rempty, GE + ((NRS + 2) & 3) * 8);
#pragma unroll 1
          for (int i = NRS; i < 14; i++) {
            mbar_wait(xfull + (i & 3) * 8, (i >> 2) & 1);
            mbar_wait(gfull + (i & 3) * 8, (i >> 2) & 1);
            const uint32_t xa = base + (i & 3) * GST_BYTES;
            const uint64_t da = make_desc(xa + wg * 8192, 16, 1024), db = make_desc(xa + UNIT, 8192, 1024);
            if (i == 13) bar_sync(2 + wg, 256);
            wg_fence();
#pragma unroll
            for (int kk = 0; kk < 4; kk++) mma256_ss(ga, gb, da + kk * 2, db + kk * 128, 1);
            wg_commit();
            if (i == 13) bar_arrive(3 - wg, 256);
            wg_wait<1>();
            uint32_t z = zero;
#pragma unroll
            for (int k = 0; k < 16; k += 2) asm volatile("lop3.b32 %0, %1, %2, %0, 0xA8;" : "+r"(z) : "r"(a[1][k]), "r"(a[1][k + 1]));
            mbar_arrive_cl(rempty, GE + ((i + 3) & 3) * 8 + z);
            mbar_arrive_pred(xempty + ((i + 3) & 3) * 8, l == 0 && i != NRS);
          }
          mbar_wait(xfull + 16, 1);
          wg_wait<0>();
          keep(ga); keep(gb);
#pragma unroll
          for (int i = 0; i < 64; i++) {
            asm volatile("mov.b32 %0, %1;" : "=f"(s[i]) : "f"(ga[i]));
            asm volatile("mov.b32 %0, %1;" : "=f"(o[i]) : "f"(gb[i]));
          }
        } else {
          float ga[64], gb[64];
#pragma unroll
          for (int i = 0; i < 64; i++) {
            asm volatile("mov.b32 %0, %1;" : "=f"(ga[i]) : "f"(s[i]));
            asm volatile("mov.b32 %0, %1;" : "=f"(gb[i]) : "f"(o[i]));
          }
#pragma unroll 1
          for (int i = 0; i < nst; i++) {
            mbar_wait(gfull + (i & 3) * 8, (i >> 2) & 1);
            const uint64_t da = make_desc(base + unit_of(xt, i & 3) + wg * 8192, 16, 1024), db = make_desc(base + unit_of(wt, i & 3), 8192, 1024);
            if (i == nst - 1) bar_sync(2 + wg, 256);
            wg_fence();
#pragma unroll
            for (int kk = 0; kk < 4; kk++) mma256_ss(ga, gb, da + kk * 2, db + kk * 128, kk ? 1 : i);
            wg_commit();
            if (i == nst - 1) bar_arrive(3 - wg, 256);
            wg_wait<1>();
            mbar_arrive_cl(rempty, GE + ((i + 3) & 3) * 8, i != 0);
            PROF(4, tid == 0 && (i & 3) == 0, 40 + (ps - 1) * 4 + i / 4);
          }
          wg_wait<0>();
          keep(ga); keep(gb);
#pragma unroll
          for (int i = 0; i < 64; i++) {
            asm volatile("mov.b32 %0, %1;" : "=f"(s[i]) : "f"(ga[i]));
            asm volatile("mov.b32 %0, %1;" : "=f"(o[i]) : "f"(gb[i]));
          }
        }
        mbar_arrive_cl(rempty, GE + (ps == 2 ? 24 : 8));
        if (ps == 2) break;
      }
      const uint32_t qw = base + wg * 8192, qt = QT >> (16 * ps), at = ps ? AT1 : AT0;
      {
        const uint32_t wt = ps ? WT1 : WT0;
        const uint64_t da0 = make_desc(qw + unit_of(qt, 2), 16, 1024), da1 = make_desc(qw + unit_of(qt, 3), 16, 1024);
        const uint64_t db0 = make_desc(base + unit_of(wt, 2), 8192, 1024), db1 = make_desc(base + unit_of(wt, 3), 8192, 1024);
        mbar_wait(gfull + 16, 1);
        bar_sync(2 + wg, 256);
        wg_fence();
#pragma unroll
        for (int kk = 0; kk < 4; kk++) mma_ss<1>(s, da0 + kk * 2, db0 + kk * 128, 1);
        wg_commit();
        mbar_wait(xfull + 24, 1);
        mbar_wait(gfull + 24, 1);
        wg_fence();
#pragma unroll
        for (int kk = 0; kk < 4; kk++) mma_ss<1>(s, da1 + kk * 2, db1 + kk * 128, 1);
        wg_commit();
        bar_arrive(3 - wg, 256);
        mbar_wait(ps == 0 ? bar_pread : bar_ofree + 8, 0);
        wg_wait<0>();
        keep(s);
        PROF(2, tid == 0, 8 + ps * 8);
        uint32_t q[32];
        pack_p(s, q);
#pragma unroll
        for (int i = 0; i < 4; i++) stmatrix4((qw + unit_of(qt, 0) + frag_offset(warp)) ^ (i << 5), q[4 * i], q[4 * i + 1], q[4 * i + 2], q[4 * i + 3]);
        keep(q);
        bar_sync(2 + wg, 256);
        wg_fence();
#pragma unroll
        for (int kk = 0; kk < 8; kk++) mma_ss<1>(o, (kk < 4 ? da0 : da1) + (kk & 3) * 2, (kk < 4 ? db0 : db1) + UNIT / 16 + (kk & 3) * 128, 1);
        wg_commit();
        mbar_wait(bfull, 0);
        wg_fence();
        const uint64_t dk = make_desc(base + unit_of(at, 0), 16, 1024);
#pragma unroll
        for (int kk = 0; kk < 8; kk++) mma_rs<0>(s, q[4 * kk], q[4 * kk + 1], q[4 * kk + 2], q[4 * kk + 3], dk + (kk >> 2) * 1024 + (kk & 3) * 2, kk != 0);
        wg_commit();
        bar_arrive(3 - wg, 256);
#pragma unroll
        for (int i = 4; i < 8; i++) stmatrix4((qw + unit_of(qt, 1) + frag_offset(warp)) ^ ((i & 3) << 5), q[4 * i], q[4 * i + 1], q[4 * i + 2], q[4 * i + 3]);
        wg_wait<1>();
        keep(o);
        mbar_arrive_cl(rempty, GE + 16);
        mbar_arrive_cl(rempty, GE + 24);
        store_chunk<0>(o, qw + unit_of(qt, 2) + frag_offset(warp));
        store_chunk<1>(o, qw + unit_of(qt, 3) + frag_offset(warp));
        wg_wait<0>();
        keep(s);
        mbar_arrive_cl(rempty, 0);
      }
      PROF(4, tid == 0 && ps == 1, 61);
      float l0 = 0.f, l1 = 0.f, f0 = 0.f, f1 = 0.f;
      auto step = [&](auto odd_c, const int j, uint32_t (&pw)[32], uint32_t (&pr)[32]) {
        constexpr bool ODD = decltype(odd_c)::value;
        const bool first = !ODD && (j & 2) == 0, last = ODD && j == 7;
        const uint32_t ph = (j >> 1) & 1;
        float i0, i1, a0, a1;
        const bool so = !ODD && j == 4;
        if (so) { i0 = inv_quad_sum(l0); i1 = inv_quad_sum(l1); l0 = 0.f; l1 = 0.f; }
        if (first) {
          int m0 = max(__float_as_int(s[0]), __float_as_int(s[1])), m1 = max(__float_as_int(s[2]), __float_as_int(s[3]));
#pragma unroll
          for (int i = 1; i < 16; i++) {
            m0 = __vimax3_s32(m0, __float_as_int(s[4 * i]), __float_as_int(s[4 * i + 1]));
            m1 = __vimax3_s32(m1, __float_as_int(s[4 * i + 2]), __float_as_int(s[4 * i + 3]));
          }
          m0 = max(m0, __shfl_xor_sync(0xffffffffu, m0, 1)); m1 = max(m1, __shfl_xor_sync(0xffffffffu, m1, 1));
          m0 = max(m0, __shfl_xor_sync(0xffffffffu, m0, 2)); m1 = max(m1, __shfl_xor_sync(0xffffffffu, m1, 2));
          f0 = fmaf(__int_as_float(m0), SCL2, BIAS); f1 = fmaf(__int_as_float(m1), SCL2, BIAS);
        }
        bool redo = false;
        while (true) {
          if (redo) {
            float m0 = fmaxf(s[0], s[1]), m1 = fmaxf(s[2], s[3]);
#pragma unroll
            for (int i = 1; i < 16; i++) { m0 = fmaxf(m0, fmaxf(s[4 * i], s[4 * i + 1])); m1 = fmaxf(m1, fmaxf(s[4 * i + 2], s[4 * i + 3])); }
            m0 = fmaxf(m0, __shfl_xor_sync(0xffffffffu, m0, 1)); m1 = fmaxf(m1, __shfl_xor_sync(0xffffffffu, m1, 1));
            m0 = fmaxf(m0, __shfl_xor_sync(0xffffffffu, m0, 2)); m1 = fmaxf(m1, __shfl_xor_sync(0xffffffffu, m1, 2));
            m0 = fmaf(m0, SCL2, BIAS); m1 = fmaf(m1, SCL2, BIAS);
            if (!first) {
              m0 = fmaxf(m0, f0); m1 = fmaxf(m1, f1);
              const float c0 = ex2(f0 - m0), c1 = ex2(f1 - m1);
              l0 *= c0; l1 *= c1;
              wg_wait<0>();
              keep(o);
#pragma unroll
              for (int i = 0; i < 16; i++) { o[4 * i] *= c0; o[4 * i + 1] *= c0; o[4 * i + 2] *= c1; o[4 * i + 3] *= c1; }
            }
            f0 = m0; f1 = m1;
          }
          float b0 = 0.f, b1 = 0.f;
          a0 = 0.f; a1 = 0.f;
#pragma unroll
          for (int i = 0; i < 16; i++) {
            const float e0 = ex2(fmaf(s[4 * i], SCL2, -f0)), e1 = ex2(fmaf(s[4 * i + 1], SCL2, -f0));
            const float e2 = ex2(fmaf(s[4 * i + 2], SCL2, -f1)), e3 = ex2(fmaf(s[4 * i + 3], SCL2, -f1));
            a0 += e0; b0 += e1; a1 += e2; b1 += e3;
            pw[2 * i] = pack_bf(e0, e1); pw[2 * i + 1] = pack_bf(e2, e3);
            if (i == VREL) {
#pragma unroll
              for (int k = 0; k < 2 * VREL + 2; k++) asm volatile("" : "+r"(pw[k])::"memory");
              mbar_wait(bar_mod, 0);
              wg_wait<0>();
              mbar_arrive_cl(rempty, ODD ? 16 : 0, !redo && (ODD || j));
#pragma unroll
              for (int k = 4 * VREL + 4; k < 64; k++) asm volatile("" : "+f"(s[k])::"memory");
            }
          }
          a0 += b0; a1 += b1;
          if (redo) break;
          redo = __any_sync(0xffffffffu, !(a0 + a1 < 1.f));
          if (!redo) break;
        }
        l0 += a0; l1 += a1;
        keep(pw);
        keep(o);
        if (so) store_chunk<0>(o, i0, i1, qw + unit_of(qt, 0) + frag_offset(warp));
        keep(o);
        if (j == (ODD ? 5 : 0)) { fence_async_smem(); if (ODD) mbar_arrive(bar_ofull + wg * 8); }
        mbar_wait(bfull + (ODD ? 24 : 8), ph);
        bar_sync(2 + wg, 256);
        if (!last) {
          const uint32_t qn = qt >> (j >= 3 ? 8 : 0);
          wg_fence();
          issue_qk(s, qw + unit_of(qn, 0), qw + unit_of(qn, 1), base + unit_of(at, ODD ? 3 : 1));
          wg_commit();
          mbar_wait(bfull + (ODD ? 0 : 16), ODD ? ph ^ 1 : ph);
        }
        if (so) { store_chunk<1>(o, i0, i1, qw + unit_of(qt, 1) + frag_offset(warp)); keep(o); }
        wg_fence();
        issue_pv(o, pw, base + unit_of(at, ODD ? (last ? 3 : 0) : 2), !first);
        wg_commit();
        bar_arrive(3 - wg, 256);
        wg_wait<1>();
        keep(s);
        mbar_arrive_cl(rempty, ODD ? 24 : 8, !last);
        PROF(4, tid == 0 && ps == 1, 51 + j);
      };
      uint32_t pa[32], pb[32];
#pragma unroll 1
      for (int j = 0; j < 8; j += 2) {
        step(std::false_type{}, j, pa, pb);
        step(std::true_type{}, j + 1, pb, pa);
      }
      {
        const float i0 = inv_quad_sum(l0), i1 = inv_quad_sum(l1);
        wg_wait<0>();
        keep(o);
        mbar_arrive_cl(rempty, 24);
        store_chunk<0>(o, i0, i1, qw + unit_of(qt, 2) + frag_offset(warp));
        store_chunk<1>(o, i0, i1, qw + unit_of(qt, 3) + frag_offset(warp));
        fence_async_smem();
        mbar_arrive(bar_ofull + 16 + wg * 8);
      }
      PROF(2, tid == 0, 10 + ps * 8);
    }

    const int ln = fresh_lane(), g = ln >> 2, tq = ln & 3, ct = warp * 32 + ln;
    const bool lane0 = ln == 0;
    const int lrow0 = warp * 16 + g;
    const uint32_t res = base + OFF_RES, trow = res + wg * 8192 + frag_offset(warp);
    uint32_t xr[32];
    uint4 sv[4], own;
    uint32_t* const sg = g_stats + (rb * 8 + warp) * 512 + g * 4;
    uint32_t* sp[4];
#pragma unroll
    for (int k = 0; k < 4; k++) sp[k] = sg + (tq & 1) * 32 + (((tq >> 1) ^ (cj >> 2)) * 4 + (k ^ (cj & 3))) * 64;
    {
      const uint64_t da = make_desc(base + wg * 8192, 16, 1024), db = make_desc(base, 8192, 1024);
      constexpr int U = UNIT / 16;
#define HALF_STAGE(acc, xu, wu) _Pragma("unroll") for (int kk = 0; kk < 4; kk++) mma_ss<1>(acc, da + (xu) * U + kk * 2, db + (wu) * U + kk * 128, 1)
      PROF(10, ct == PT, 19); STAMP(0);
      cluster_arrive();
      mbar_wait(gfull, 1);
      mbar_wait(gfull + 8, 1);
      bar_sync(2 + wg, 256);
      wg_fence();
      HALF_STAGE(o, 7, 1);
      HALF_STAGE(o, 8, 3);
      wg_commit();
      STAMP(16);
      mbar_wait(gfull + 16, 1);
      STAMP(17);
      wg_fence();
      HALF_STAGE(o, 6, 11);
      wg_commit();
      bar_arrive(3 - wg, 256);
      mbar_wait(bar_par, 0);
      uint32_t* xo = g_xch + ((size_t)b * 8 * 256 + ct) * 4;
      const uint32_t* xi = g_xch + ((size_t)(b ^ 2) * 8 * 256 + ct) * 4;
      const uint32_t par1 = (~lds1(par + PAR_CONST + 4) & 1) << 16;
      wg_wait<1>();
      mbar_arrive_pred(bar_rel, lane0);
      wg_wait<0>();
      keep(o);
      mbar_arrive_pred(bar_ring, lane0);
      PROF(8, ct == PT, 20); STAMP(1);
#define SEND(i) st_b128(xo + (i) * 1024, (pack_bf(o[8 * (i)], o[8 * (i) + 1]) & ~0x10000u) | par1, pack_bf(o[8 * (i) + 2], o[8 * (i) + 3]), \
                        pack_bf(o[8 * (i) + 4], o[8 * (i) + 5]), pack_bf(o[8 * (i) + 6], o[8 * (i) + 7]))
#pragma unroll
      for (int i = 0; i < NS1; i++) SEND(i);
      PROF(8, ct == PT, 21); STAMP(2);
      bar_sync(2 + wg, 256);
      wg_fence();
      HALF_STAGE(s, 7, 0);
      HALF_STAGE(s, 8, 2);
      HALF_STAGE(s, 6, 10);
      wg_commit();
      bar_arrive(3 - wg, 256);
      STAMP(18);
      mbar_wait(gfull + 24, 1);
#pragma unroll
      for (int i = NS1; i < 8; i++) SEND(i);
      uint4 v[8];
      STAMP(19);
      mbar_wait(bar_xres, 0);
      wg_wait<0>();
      mbar_arrive_pred(bar_ring + 8, lane0);
      bar_sync(2 + wg, 256);
      STAMP(20);
#pragma unroll
      for (int i = 0; i < LD2; i++) v[i] = ld_b128(xi + i * 1024);
      mbar_wait(bar_xres, 0);
      wg_fence();
      HALF_STAGE(s, 9, 4);
      wg_commit();
      mbar_wait(bar_rx, 0);
      wg_fence();
      HALF_STAGE(s, 1, 5);
      wg_commit();
      bar_arrive(3 - wg, 256);
      STAMP(21);
#pragma unroll
      for (int i = LD2; i < 8; i++) v[i] = ld_b128(xi + i * 1024);
      mbar_wait(bar_xres, 0);
      wg_wait<0>();
      keep(s);
      mbar_arrive_pred(bar_ring + 16, lane0);
      PROF(10, ct == PT, 23); STAMP(4);
#pragma unroll
      for (int i = 0; i < 16; i += 2) ldmatrix4((trow ^ ((i & 7) << 4)) + (i >> 3) * 16384, xr[2 * i], xr[2 * i + 1], xr[2 * i + 2], xr[2 * i + 3]);
      uint32_t ga[16];
      uint4 bw[8];
#pragma unroll
      for (int i = 0; i < 8; i++) {
        if (!(i & 1)) {
          const uint4 t = lds4(par + PAR_SINK + i * 32 + tq * 16);
          ga[2 * i] = t.x; ga[2 * i + 1] = t.y; ga[2 * i + 2] = t.z; ga[2 * i + 3] = t.w;
        }
        bw[i] = lds4(par + PAR_T1 + i * 64 + tq * 16);
        if (!(g & 1)) { bw[i].x = 0x3f803f80u; bw[i].y = 0x3f803f80u; }
      }
      uint32_t pk[32];
      pack_p(s, pk);
      const uint32_t par2 = (~lds1(par + PAR_CONST + 12) & 1) << 16;
      {
        uint32_t n = 0, miss;
        do {
          miss = 0;
#pragma unroll
          for (int i = 0; i < 8; i++) miss |= v[i].x ^ par2;
          miss = __any_sync(0xffffffffu, miss & 0x10000u);
          if (miss) {
#pragma unroll
            for (int i = 0; i < 8; i++)
              asm volatile("{ .reg .pred p; .reg .b32 t; xor.b32 t, %0, %5; and.b32 t, t, 0x10000; setp.ne.u32 p, t, 0;\n"
                           "@p ld.relaxed.gpu.global.v4.u32 {%0, %1, %2, %3}, [%4]; }"
                           : "+r"(v[i].x), "+r"(v[i].y), "+r"(v[i].z), "+r"(v[i].w) : "l"(xi + i * 1024), "r"(par1) : "memory");
          }
          watchdog(n);
        } while (miss);
      }
      PROF(8, ct == PT, 22); STAMP(3);
      float ds[4] = {0.f, 0.f, 0.f, 0.f}, dl[4] = {0.f, 0.f, 0.f, 0.f}, q0[4] = {0.f, 0.f, 0.f, 0.f}, q1[4] = {0.f, 0.f, 0.f, 0.f};
#pragma unroll
      for (int i = 0; i < 8; i++) {
        const uint32_t u0 = hfma2(ga[2 * i], hadd2(pk[4 * i], v[i].x & ~0x10000u), xr[4 * i]);
        const uint32_t u1 = hfma2(ga[2 * i], hadd2(pk[4 * i + 1], v[i].y), xr[4 * i + 1]);
        const uint32_t u2 = hfma2(ga[2 * i + 1], hadd2(pk[4 * i + 2], v[i].z), xr[4 * i + 2]);
        const uint32_t u3 = hfma2(ga[2 * i + 1], hadd2(pk[4 * i + 3], v[i].w), xr[4 * i + 3]);
        xr[4 * i] = u0; xr[4 * i + 1] = u1; xr[4 * i + 2] = u2; xr[4 * i + 3] = u3;
        mma16816(ds, u0, u1, u2, u3, bw[i].x, bw[i].y);
        mma16816(dl, u0, u1, u2, u3, bw[i].z, bw[i].w);
        mma16816(q0, u0, u1, u2, u3, u0, u2);
        mma16816(q1, u0, u1, u2, u3, u1, u3);
      }
      const float sqa = (g & 1) ? q0[1] : q0[0], sqb = (g & 1) ? q1[3] : q1[2], dta = ds[1] + dl[1], dtb = ds[3] + dl[3];
      if (tq == (g >> 1)) {
        st_b128(sg + cj * 64, __float_as_uint(ds[0]), __float_as_uint(sqa), __float_as_uint(dta), tag);
        st_b128(sg + cj * 64 + 32, __float_as_uint(ds[2]), __float_as_uint(sqb), __float_as_uint(dtb), tag);
      }
#pragma unroll
      for (int k = 0; k < 4; k++) sv[k] = ld_b128(sp[k]);
      mbar_wait(bar_xres, 0);
      const float sqc = __shfl_sync(0xffffffffu, sqa, g * 4 + (g >> 1)), sqd = __shfl_sync(0xffffffffu, sqb, g * 4 + (g >> 1));
      own = (tq & 1) ? make_uint4(__float_as_uint(ds[2]), __float_as_uint(sqd), __float_as_uint(dtb), tag)
                     : make_uint4(__float_as_uint(ds[0]), __float_as_uint(sqc), __float_as_uint(dta), tag);
    }
    PROF(8, ct == PT, 29); STAMP(5);
    uint32_t mm, ih, il;
    float rbest;
    uint32_t wf[128];
    const uint32_t frow = (ln & 7) + (ln >> 4) * 8;
    const uint32_t wfo = base + (warp & 1) * 8192 + frow * 64 + ((((ln >> 3) & 1) ^ ((frow >> 1) & 3)) << 4);
#define LOAD_WF(m) _Pragma("unroll") for (int f = 0; f < 16; f++) {                                                   \
      const int r = ((f >> 1) * 4 + (m) * 2 + (f & 1)) * 4;                                                           \
      ldmatrix4t(((wfo + unit_of((m) ? FT_U : FT_G, warp >> 1)) ^ ((f & 1) * 32)) + (f >> 1) * 1024, wf[r], wf[r + 1], wf[r + 2], wf[r + 3]); \
    }
    bool early;
    {
#pragma unroll
      for (int i = 0; i < 16; i += 2) stmatrix4((trow ^ ((i & 7) << 4)) + (i >> 3) * 16384, xr[2 * i], xr[2 * i + 1], xr[2 * i + 2], xr[2 * i + 3]);
      const uint4 cst = lds4(par + PAR_CONST);
      const float A1 = __uint_as_float(cst.x), A2 = __uint_as_float(cst.z);
      uint32_t n = 0;
      early = false;
#pragma unroll 1
      while (true) {
        if (!early && (b >= NFFN || __all_sync(0xffffffffu, mbar_test(bar_box + (warp >> 1) * 8, 0)))) {
          early = true;
          LOAD_WF(0);
          __syncwarp();
          mbar_arrive_pred(bar_gate, lane0);
        }
        uint32_t miss;
        asm volatile("{ .reg .pred p0, p1, p2, p3; .reg .b64 u, v; .reg .b128 w;\n"
                     "setp.ge.u32 p0, %22, 2; setp.ne.and.u32 p0, %4, %21, p0; setp.ne.u32 p1, %8, %21; setp.ne.u32 p2, %12, %21; setp.ne.u32 p3, %16, %21;\n"
                     "@p0 ld.relaxed.gpu.global.v4.u32 {%1, %2, %3, %4}, [%17];\n"
                     "@p1 ld.relaxed.gpu.global.v4.u32 {%5, %6, %7, %8}, [%18];\n"
                     "@p2 ld.relaxed.gpu.global.v4.u32 {%9, %10, %11, %12}, [%19];\n"
                     "@p3 ld.relaxed.gpu.global.v4.u32 {%13, %14, %15, %16}, [%20];\n"
                     "or.pred p0, p0, p1; or.pred p2, p2, p3; or.pred p0, p0, p2; vote.sync.any.pred p0, p0, 0xffffffff; selp.u32 %0, 1, 0, p0; }"
                     : "=r"(miss), "+r"(sv[0].x), "+r"(sv[0].y), "+r"(sv[0].z), "+r"(sv[0].w), "+r"(sv[1].x), "+r"(sv[1].y), "+r"(sv[1].z), "+r"(sv[1].w),
                       "+r"(sv[2].x), "+r"(sv[2].y), "+r"(sv[2].z), "+r"(sv[2].w), "+r"(sv[3].x), "+r"(sv[3].y), "+r"(sv[3].z), "+r"(sv[3].w)
                     : "l"(sp[0]), "l"(sp[1]), "l"(sp[2]), "l"(sp[3]), "r"(tag), "r"(tq) : "memory");
        if (!miss) break;
        watchdog(n);
      }
      const uint4 v0 = tq < 2 ? own : sv[0], v1 = sv[1], v2 = sv[2], v3 = sv[3];
      PROF(8, ct == PT, 30); STAMP(6);
      float su = (__uint_as_float(v0.x) + __uint_as_float(v1.x)) + (__uint_as_float(v2.x) + __uint_as_float(v3.x));
      float sq = (__uint_as_float(v0.y) + __uint_as_float(v1.y)) + (__uint_as_float(v2.y) + __uint_as_float(v3.y));
      float dt = (__uint_as_float(v0.z) + __uint_as_float(v1.z)) + (__uint_as_float(v2.z) + __uint_as_float(v3.z));
      su += __shfl_xor_sync(0xffffffffu, su, 2); sq += __shfl_xor_sync(0xffffffffu, sq, 2); dt += __shfl_xor_sync(0xffffffffu, dt, 2);
      const float m = su * (1.f / DM);
      float mb, sd;
      ln_scalars(m, fmaxf(sq * (1.f / DM) - m * m, 0.f), mb, sd);
      const float inv = rcp(sd);
      rbest = (dt - mb * A1) * inv + A2;
      mm = pack_bf(mb, mb);
      ih = pack_bf(inv, inv);
      const float lo = inv - bf_lo(ih);
      il = pack_bf(lo, lo);
    }
    int ibest;
    {
      const uint32_t bits = __float_as_uint(rbest);
      const uint32_t key = (((int)bits < 0 ? ~bits : bits | 0x80000000u) & ~0x1ffu) | ((127 - lrow0 - (tq & 1) * 8) << 2) | tag;
      sts1(par + PAR_RED + warp * 4, __reduce_max_sync(0xffffffffu, key));
      PROF(8, ct == PT, 38); STAMP(7);
      bar_sync(1, 256);
      const uint4 ka = lds4(par + PAR_RED), kb = lds4(par + PAR_RED + 16);
      const uint32_t k2 = max(max(max(ka.x, ka.y), max(ka.z, ka.w)), max(max(kb.x, kb.y), max(kb.z, kb.w)));
      if (ct < CR && cj == 0) st_relaxed(g_cand + ct * 512 + rb * CS, k2);
      ibest = 127 - ((k2 >> 2) & 127);
    }
    PROF(8, ct == PT, 39); STAMP(8);
    if ((ibest >> 4) == warp) {
      const int src = (ibest & 7) * 4 + ((ibest >> 3) & 1), ch = g * 2;
      const uint32_t cm = __shfl_sync(0xffffffffu, mm, src), ch_ = __shfl_sync(0xffffffffu, ih, src), cl = __shfl_sync(0xffffffffu, il, src);
      const uint32_t xa = res + (ch >> 3) * 16384 + ibest * 128 + (((ch & 7) ^ (ibest & 7)) << 4) + tq * 4;
      const uint32_t x0 = lds1(xa), x1 = lds1(xa ^ 16);
      const uint2 p0 = lds2(par + PAR_T2 + ch * 64 + tq * 16), p1 = lds2(par + PAR_T2 + ch * 64 + 64 + tq * 16);
      uint32_t* dst = g_row + rb * 2 * DM + cj * 128 + ln * 4;
      st_pairs(dst, ln_mod(x0, cm, ch_, cl, p0.x, p0.y), ln_mod(x1, cm, ch_, cl, p1.x, p1.y), tag);
      st_pairs(dst + DM, x0, x1, tag);
      __syncwarp();
    }
    PROF(8, ct == PT, 37); STAMP(9);
    uint32_t wd[64];
    const uint32_t wda = base + unit_of(FT_D, warp >> 1) + (warp & 1) * 8192 + frow * 128 + ((((ln >> 3) & 1) ^ (ln & 7)) << 4);
#define LOAD_WD(f) ldmatrix4t((wda ^ ((((f) >> 1) & 3) * 32)) + ((f) >> 3) * 4096 + ((f) & 1) * 2048, wd[4 * (f)], wd[4 * (f) + 1], wd[4 * (f) + 2], wd[4 * (f) + 3])
    if (!early) {
      if (b < NFFN) mbar_wait(bar_box + (warp >> 1) * 8, 0);
      LOAD_WF(0);
      __syncwarp();
      mbar_arrive_pred(bar_gate, lane0);
    }
    if (b < NFFN) {
      const uint32_t own = base + unit_of(FT_G, warp >> 1) + (warp & 1) * 8192;
      mbar_wait(bar_box + (4 + (warp >> 1)) * 8, 0);
      LOAD_WF(1);
      uint32_t* const ydst = ypart_slot(b, warp * 16 + (tq & 1) * 8 + g);
      PROF(8, ct == PT, 31); STAMP(10);
      bool wdok;
      {
        uint32_t n = 0;
        while (!(wdok = __all_sync(0xffffffffu, mbar_test(bar_box + (8 + (warp >> 1)) * 8, 0))) && !__all_sync(0xffffffffu, mbar_test(bar_sel, 0))) watchdog(n);
      }
      if (wdok) {
#pragma unroll
        for (int f = 0; f < 16; f++) LOAD_WD(f);
      }
      STAMP(11);
      mbar_wait(bar_sel, 0);
      PROF(8, ct == PT, 33); STAMP(12);
      float d[8][4];
#pragma unroll
      for (int i = 0; i < 4; i++) { d[i][0] = 0.f; d[i][1] = 0.f; d[i][2] = 0.f; d[i][3] = 0.f; }
#pragma unroll
      for (int ks = 0; ks < 8; ks++) {
        const uint2 hb = lds2(own + 256 + ks * 32 + tq * 8);
#pragma unroll
        for (int mt = 0; mt < 4; mt++) {
          const int r = ks * 16 + mt * 4;
          mma16816(d[mt], wf[r], wf[r + 1], wf[r + 2], wf[r + 3], hb.x, hb.y);
        }
      }
      sts2(own + (tq * 8 + g) * 8, __float_as_uint((tq & 2) ? ((tq & 1) ? d[1][2] : d[1][0]) : ((tq & 1) ? d[0][2] : d[0][0])),
           __float_as_uint((tq & 2) ? ((tq & 1) ? d[3][2] : d[3][0]) : ((tq & 1) ? d[2][2] : d[2][0])));
      bar_sync(1, 256);
      uint32_t ab[4];
      {
        float G = 0.f, U = 0.f;
        uint2 pv[8];
#pragma unroll
        for (int w8 = 0; w8 < 8; w8++) pv[w8] = lds2(base + ln * 8 + ((FT_G >> (w8 >> 1) * 4) & 15) * UNIT + (w8 & 1) * 8192);
#pragma unroll
        for (int w8 = 0; w8 < 8; w8 += 2) {
          G += __uint_as_float(pv[w8].x) + __uint_as_float(pv[w8 + 1].x);
          U += __uint_as_float(pv[w8].y) + __uint_as_float(pv[w8 + 1].y);
        }
        const float act = rbf(silu_f(rbf(G))) * rbf(U);
        const uint32_t pk = pack_bf(act, __shfl_down_sync(0xffffffffu, act, 1));
#pragma unroll
        for (int i = 0; i < 4; i++) ab[i] = __shfl_sync(0xffffffffu, pk, i * 8 + tq * 2);
      }
      if (!wdok) {
        mbar_wait(bar_box + (8 + (warp >> 1)) * 8, 0);
#pragma unroll
        for (int f = 0; f < 16; f++) LOAD_WD(f);
      }
      PROF(8, ct == PT, 34); STAMP(13);
#pragma unroll
      for (int mt = 0; mt < 8; mt++) {
        d[mt][0] = 0.f; d[mt][1] = 0.f; d[mt][2] = 0.f; d[mt][3] = 0.f;
        mma16816(d[mt], wd[mt * 8], wd[mt * 8 + 1], wd[mt * 8 + 2], wd[mt * 8 + 3], ab[0], ab[1]);
        mma16816(d[mt], wd[mt * 8 + 4], wd[mt * 8 + 5], wd[mt * 8 + 6], wd[mt * 8 + 7], ab[2], ab[3]);
      }
      uint32_t yw[4];
#pragma unroll
      for (int i = 0; i < 4; i++) yw[i] = (tq & 1) ? pack_bf(d[2 * i][2], d[2 * i + 1][2]) : pack_bf(d[2 * i][0], d[2 * i + 1][0]);
      if (tq < 2) st_b128(ydst, (yw[0] & ~1u) | (tag & 1), (yw[1] & ~1u) | (tag >> 1), yw[2], yw[3]);
      PROF(8, ct == PT, 35); STAMP(14);
    }
    mbar_wait(bar_sel, 0);
    mbar_arrive_pred(bar_win, ct == 0);
    const int iwin = lds1(par + PAR_CONST + 60) & 0x7ff;
    const bool cand = (iwin >> 4) == rb * 8 + warp;
    {
      const uint32_t mm0 = __shfl_sync(0xffffffffu, mm, ln & ~1), mm1 = __shfl_sync(0xffffffffu, mm, ln | 1);
      const uint32_t ih0 = __shfl_sync(0xffffffffu, ih, ln & ~1), ih1 = __shfl_sync(0xffffffffu, ih, ln | 1);
      const uint32_t il0 = __shfl_sync(0xffffffffu, il, ln & ~1), il1 = __shfl_sync(0xffffffffu, il, ln | 1);
#pragma unroll 1
      for (int hf = 0; hf < 2; hf++) {
        uint32_t x[16];
#pragma unroll
        for (int i = 0; i < 8; i += 2) ldmatrix4((trow ^ (i << 4)) + hf * 16384, x[2 * i], x[2 * i + 1], x[2 * i + 2], x[2 * i + 3]);
#pragma unroll
        for (int i = 0; i < 8; i++) {
          const uint4 pv = lds4(par + PAR_T2 + (hf * 8 + i) * 64 + tq * 16);
          x[2 * i] = hfma2(hfma2(ln_norm(x[2 * i], mm0, ih0, il0), pv.x, pv.y), pv.z, x[2 * i]);
          x[2 * i + 1] = hfma2(hfma2(ln_norm(x[2 * i + 1], mm1, ih1, il1), pv.x, pv.y), pv.z, x[2 * i + 1]);
        }
#pragma unroll
        for (int i = 0; i < 8; i += 2) stmatrix4((trow ^ (i << 4)) + hf * 16384, x[2 * i], x[2 * i + 1], x[2 * i + 2], x[2 * i + 3]);
        if (!cand) fence_async_smem();
        __syncwarp();
        if (!cand && elect_one()) {
          tma2d_store(&maps.out, res + hf * 16384 + warp * 2048, cj * 128 + hf * 64, rb * 128 + warp * 16);
          asm volatile("cp.async.bulk.commit_group;" ::: "memory");
        }
      }
    }
    if (cand) {
      const int wrow0 = warp * 16;
#pragma unroll 2
      for (int p = 0; p < 8; p++) {
        const int row = 2 * p + (ln >> 4), ch = ln & 15;
        const uint4 v = lds4(res + (ch >> 3) * 16384 + (wrow0 + row) * 128 + (((ch & 7) ^ (row & 7)) << 4));
        if (rb * 128 + wrow0 + row != iwin) *reinterpret_cast<uint4*>(P.out + (size_t)(rb * 128 + wrow0 + row) * DM + cj * 128 + ch * 8) = v;
      }
    }
    asm volatile("cp.async.bulk.wait_group.read 0;" ::: "memory");
    PROF(8, ct == PT, 11); STAMP(15);
    cluster_wait();
  }
}

typedef CUresult (*EncodeFn)(CUtensorMap*, CUtensorMapDataType, cuuint32_t, void*, const cuuint64_t*, const cuuint64_t*,
                             const cuuint32_t*, const cuuint32_t*, CUtensorMapInterleave, CUtensorMapSwizzle,
                             CUtensorMapL2promotion, CUtensorMapFloatOOBfill);

void map2d(EncodeFn enc, CUtensorMap* m, const void* p, uint64_t rows, uint64_t cols, uint32_t brows) {
  cuuint64_t dims[2] = {cols, rows}, strides[1] = {cols * 2};
  cuuint32_t box[2] = {64, brows}, es[2] = {1, 1};
  enc(m, CU_TENSOR_MAP_DATA_TYPE_BFLOAT16, 2, const_cast<void*>(p), dims, strides, box, es, CU_TENSOR_MAP_INTERLEAVE_NONE,
      CU_TENSOR_MAP_SWIZZLE_128B, CU_TENSOR_MAP_L2_PROMOTION_L2_256B, CU_TENSOR_MAP_FLOAT_OOB_FILL_NONE);
}
void map2d_narrow(EncodeFn enc, CUtensorMap* m, const void* p, uint64_t rows, uint64_t cols, uint32_t brows) {
  cuuint64_t dims[2] = {cols, rows}, strides[1] = {cols * 2};
  cuuint32_t box[2] = {32, brows}, es[2] = {1, 1};
  enc(m, CU_TENSOR_MAP_DATA_TYPE_BFLOAT16, 2, const_cast<void*>(p), dims, strides, box, es, CU_TENSOR_MAP_INTERLEAVE_NONE,
      CU_TENSOR_MAP_SWIZZLE_64B, CU_TENSOR_MAP_L2_PROMOTION_L2_64B, CU_TENSOR_MAP_FLOAT_OOB_FILL_NONE);
}
void map3d(EncodeFn enc, CUtensorMap* m, const void* p, uint64_t rows, uint64_t cols, uint32_t brows, uint32_t nch) {
  cuuint64_t dims[3] = {64, rows, cols / 64}, strides[2] = {cols * 2, 128};
  cuuint32_t box[3] = {64, brows, nch}, es[3] = {1, 1, 1};
  enc(m, CU_TENSOR_MAP_DATA_TYPE_BFLOAT16, 3, const_cast<void*>(p), dims, strides, box, es, CU_TENSOR_MAP_INTERLEAVE_NONE,
      CU_TENSOR_MAP_SWIZZLE_128B, CU_TENSOR_MAP_L2_PROMOTION_L2_256B, CU_TENSOR_MAP_FLOAT_OOB_FILL_NONE);
}

}

extern "C" void kernel_launch(void* const* d_in, const int* in_sizes, int n_in, void* d_out, int out_size) {
  (void)in_sizes; (void)n_in; (void)out_size;
  static EncodeFn enc = nullptr;
  if (!enc) {
    void* fn = nullptr;
    cudaDriverEntryPointQueryResult st;
    cudaGetDriverEntryPoint("cuTensorMapEncodeTiled", &fn, cudaEnableDefault, &st);
    enc = (EncodeFn)fn;
    cudaFuncSetAttribute(fused_kernel, cudaFuncAttributeMaxDynamicSharedMemorySize, SMEM_BYTES);
  }
  Maps maps;
  map2d(enc, &maps.x, d_in[0], SEQ, DM, 128);
  map2d(enc, &maps.out, d_out, SEQ, DM, 16);
  map3d(enc, &maps.wq, d_in[3], DM, NQ, 64, 2);
  map3d(enc, &maps.k, d_in[1], 4 * SK, 128, 128, 1);
  map3d(enc, &maps.v, d_in[2], 4 * SK, 128, 128, 1);
  map3d(enc, &maps.wo, d_in[4], NQ, DM, 64, 2);
  map2d_narrow(enc, &maps.wg, d_in[7], DM, FF, 256);
  map2d_narrow(enc, &maps.wu, d_in[8], DM, FF, 256);
  map3d(enc, &maps.wd, d_in[9], FF, DM, 32, 4);
  map2d_narrow(enc, &maps.wm, d_in[11], DM, NMOD, 256);
  Ptrs p;
  p.x = (const __nv_bfloat16*)d_in[0];
  p.w_r = (const __nv_bfloat16*)d_in[6];
  p.w_gate = (const __nv_bfloat16*)d_in[7];
  p.w_up = (const __nv_bfloat16*)d_in[8];
  p.w_down = (const __nv_bfloat16*)d_in[9];
  p.c = (const __nv_bfloat16*)d_in[10];
  p.w_mod = (const __nv_bfloat16*)d_in[11];
  p.out = (__nv_bfloat16*)d_out;
  fused_kernel<<<NMAIN + NHELP, 384, SMEM_BYTES>>>(maps, p);
}
```

```cpp
#include <cuda_runtime.h>
#include <cuda_bf16.h>
#include <cuda.h>
#include <stdint.h>
#include <type_traits>

#define HD 2
#define HDX 2
#define NRS 8
#define OSL 900
#define OSL2 400
#define RSL 40
#define BIAS 96.f
#define GL 1
#define VREL 5
#define OPS 8192
#define ODS1 5
#define ODS 7
#define PG0 15
#define WB 2
#define WN 20
#define HU 32
#define RES0 17
#define RES1 20
#define GOST 20
#define NS1 5
#define LD2 4
#define FPACE0 2
#define FPACE 3
#define CR 8
#define CS 8

namespace {

constexpr int SEQ = 2048, DM = 1024, NQ = 4096, SK = 2048, WIN = 512, FF = 3584, NMOD = 6144;
constexpr int NMAIN = 128, NHELP = 4, NFFN = 112;
constexpr int NSLOT = 4, SLOT_BYTES = 32768, UNIT = 16384, GST_BYTES = 3 * UNIT;
constexpr uint32_t XT1 = 0xDCBA, XT2 = 0x9687;
constexpr uint32_t WT0 = 0xA741, WT1 = 0x7420, WT2 = 0x4A20;
constexpr uint32_t AT0 = WT1, AT1 = WT2;
constexpr uint32_t QT = 0xDC9696DC;
constexpr int OFF_STAGE = 12 * UNIT;
constexpr uint32_t FT_G = 0x07B3, FT_U = 0xA628, FT_D = 0x5149;
constexpr int OFF_RES = 12 * UNIT;
constexpr int OFF_PAR = 14 * UNIT;
constexpr int OFF_BAR = OFF_PAR + 2528;
constexpr int SMEM_BYTES = OFF_BAR + 544;
static_assert(SMEM_BYTES <= 232448, "smem");

constexpr int PAR_T1 = 0;
constexpr int PAR_T2 = 512;
constexpr int PAR_CONST = 1536;
constexpr int PAR_RED = 1600;
constexpr int PAR_SINK = 2176;

struct Maps {
  CUtensorMap x, wq, k, v, wo, wg, wu, wd, wm, out;
};
struct Ptrs {
  const __nv_bfloat16 *x, *w_r, *c, *w_mod, *w_gate, *w_up, *w_down;
  __nv_bfloat16* out;
};

__device__ __align__(1024) uint8_t g_act[16 * 80 * UNIT];
__device__ __align__(128) uint32_t g_mod[NMOD];
__device__ __align__(128) uint32_t g_modp[2 * 2 * DM];
__device__ __align__(128) uint32_t g_ln1[SEQ * 4];
__device__ __align__(128) uint32_t g_cnt_h[16 * 32];
__device__ __align__(128) uint32_t g_cnt_o[128 * 32];
__device__ __align__(128) uint32_t g_xch[NMAIN * 8 * 256 * 4];
__device__ __align__(128) uint32_t g_stats[8 * SEQ * 4];
__device__ __align__(128) uint32_t g_cand[CR * 512];
__device__ __align__(128) uint32_t g_row[16 * 2 * DM];
__device__ __align__(128) uint32_t g_ypart[NMAIN * NFFN * 4];
__device__ __forceinline__ uint32_t* ypart_slot(int writer, int reader) { return g_ypart + (writer * NMAIN + reader) * 4; }
__device__ uint32_t g_epoch;

__device__ __forceinline__ uint32_t fresh_lane() { uint32_t l; asm volatile("mov.u32 %0, %%laneid;" : "=r"(l)); return l; }
__device__ __forceinline__ uint32_t frag_offset(int warp) {
  const uint32_t l = fresh_lane();
  return ((warp & 3) * 16 + (l & 15)) * 128 + (((l >> 4) ^ (l & 7)) << 4);
}
__device__ __forceinline__ bool elect_one() {
  uint32_t p;
  asm volatile("{ .reg .pred q; elect.sync _|q, 0xffffffff; selp.u32 %0, 1, 0, q; }" : "=r"(p));
  return p;
}
__device__ __forceinline__ uint32_t smem_u32(const void* p) { return (uint32_t)__cvta_generic_to_shared(p); }
__device__ __forceinline__ void mbar_init(uint32_t bar, uint32_t cnt) {
  asm volatile("mbarrier.init.shared::cta.b64 [%0], %1;" ::"r"(bar), "r"(cnt) : "memory");
}
__device__ __forceinline__ void mbar_expect_tx(uint32_t bar, uint32_t bytes) {
  asm volatile("mbarrier.arrive.expect_tx.shared::cta.b64 _, [%0], %1;" ::"r"(bar), "r"(bytes) : "memory");
}
__device__ __forceinline__ void mbar_arrive(uint32_t bar) {
  asm volatile("mbarrier.arrive.shared::cta.b64 _, [%0];" ::"r"(bar) : "memory");
}
__device__ __forceinline__ void mbar_arrive_pred(uint32_t bar, bool p) {
  asm volatile("{ .reg .pred p; setp.ne.b32 p, %1, 0; @p mbarrier.arrive.shared::cta.b64 _, [%0]; }" ::"r"(bar), "r"((int)p) : "memory");
}
__device__ __forceinline__ void mbar_arrive_cl(uint32_t bar, uint32_t off, bool p = true) {
  asm volatile("{ .reg .pred p, q; .reg .b32 a; setp.ne.b32 q, %2, 0; setp.ne.and.b32 p, %0, 0, q; add.u32 a, %0, %1; @p mbarrier.arrive.shared::cluster.b64 _, [a]; }"
               ::"r"(bar), "r"(off), "r"((int)p) : "memory");
}
__device__ __forceinline__ uint32_t mapa(uint32_t addr, uint32_t cta) {
  uint32_t r; asm("mapa.shared::cluster.u32 %0, %1, %2;" : "=r"(r) : "r"(addr), "r"(cta)); return r;
}
__device__ __forceinline__ void cluster_arrive() { asm volatile("barrier.cluster.arrive.relaxed.aligned;" ::: "memory"); }
__device__ __forceinline__ void cluster_wait() { asm volatile("barrier.cluster.wait.aligned;" ::: "memory"); }
__device__ __forceinline__ void watchdog(uint32_t& n) {
}
__device__ __forceinline__ void mbar_wait(uint32_t bar, uint32_t parity) {
  asm volatile("{\n.reg .pred p;\nWAIT_%=:\nmbarrier.try_wait.parity.shared::cta.b64 p, [%0], %1;\n@!p bra WAIT_%=;\n}" ::"r"(bar), "r"(parity) : "memory");
}
__device__ __forceinline__ bool mbar_test(uint32_t bar, uint32_t parity) {
  uint32_t ok;
  asm volatile("{\n.reg .pred p;\nmbarrier.test_wait.parity.shared::cta.b64 p, [%1], %2;\nselp.u32 %0, 1, 0, p;\n}" : "=r"(ok) : "r"(bar), "r"(parity) : "memory");
  return ok;
}
__device__ __forceinline__ uint64_t l2_stream() {
  uint64_t f; asm("createpolicy.fractional.L2::evict_first.b64 %0, 1.0;" : "=l"(f)); return f;
}
__device__ __forceinline__ uint64_t l2_normal() {
  uint64_t f; asm("createpolicy.fractional.L2::evict_normal.b64 %0, 1.0;" : "=l"(f)); return f;
}
__device__ __forceinline__ void tma2d(uint32_t dst, const CUtensorMap* m, int c0, int c1, uint32_t bar) {
  asm volatile("cp.async.bulk.tensor.2d.shared::cluster.global.mbarrier::complete_tx::bytes.L2::cache_hint [%0], [%1, {%3, %4}], [%2], %5;"
               ::"r"(dst), "l"(m), "r"(bar), "r"(c0), "r"(c1), "l"(l2_stream()) : "memory");
}
__device__ __forceinline__ void bulk_load(uint32_t dst, const void* src, uint32_t bytes, uint32_t bar) {
  asm volatile("cp.async.bulk.shared::cluster.global.mbarrier::complete_tx::bytes [%0], [%1], %2, [%3];" ::"r"(dst), "l"(src), "r"(bytes), "r"(bar) : "memory");
}
__device__ __forceinline__ void bulk_load_stream(uint32_t dst, const void* src, uint32_t bytes, uint32_t bar, uint64_t pol = l2_stream()) {
  asm volatile("cp.async.bulk.shared::cluster.global.mbarrier::complete_tx::bytes.L2::cache_hint [%0], [%1], %2, [%3], %4;"
               ::"r"(dst), "l"(src), "r"(bytes), "r"(bar), "l"(pol) : "memory");
}
__device__ __forceinline__ void tma2d_store(const CUtensorMap* m, uint32_t src, int c0, int c1) {
  asm volatile("cp.async.bulk.tensor.2d.global.shared::cta.bulk_group [%0, {%2, %3}], [%1];" ::"l"(m), "r"(src), "r"(c0), "r"(c1) : "memory");
}
__device__ __forceinline__ void bulk_store(void* dst, uint32_t src, uint32_t bytes) {
  asm volatile("cp.async.bulk.global.shared::cta.bulk_group [%0], [%1], %2;" ::"l"(dst), "r"(src), "r"(bytes) : "memory");
}
__device__ __forceinline__ int slice_of(int i) { return i + ((i & 7) == 1) - ((i & 7) == 2); }
__device__ __forceinline__ uint32_t unit_of(uint32_t table, uint32_t i) { return ((table >> (i * 4)) & 15) * UNIT; }
__device__ __forceinline__ void tma3d(uint32_t dst, const CUtensorMap* m, int c0, int c1, int c2, uint32_t bar) {
  asm volatile("cp.async.bulk.tensor.3d.shared::cluster.global.mbarrier::complete_tx::bytes.L2::cache_hint [%0], [%1, {%3, %4, %5}], [%2], %6;"
               ::"r"(dst), "l"(m), "r"(bar), "r"(c0), "r"(c1), "r"(c2), "l"(l2_stream()) : "memory");
}
template <bool STREAM>
__device__ __forceinline__ void tma3d_mc(uint32_t dst, const CUtensorMap* m, int c0, int c1, int c2, uint32_t bar) {
  if (STREAM)
    asm volatile("cp.async.bulk.tensor.3d.shared::cluster.global.mbarrier::complete_tx::bytes.multicast::cluster.L2::cache_hint [%0], [%1, {%3, %4, %5}], [%2], %6, %7;"
                 ::"r"(dst), "l"(m), "r"(bar), "r"(c0), "r"(c1), "r"(c2), "h"((uint16_t)3), "l"(l2_stream()) : "memory");
  else
    asm volatile("cp.async.bulk.tensor.3d.shared::cluster.global.mbarrier::complete_tx::bytes.multicast::cluster [%0], [%1, {%3, %4, %5}], [%2], %6;"
                 ::"r"(dst), "l"(m), "r"(bar), "r"(c0), "r"(c1), "r"(c2), "h"((uint16_t)3) : "memory");
}
__device__ __forceinline__ void prefetch_map(const CUtensorMap* m) {
  asm volatile("prefetch.tensormap [%0];" ::"l"(m) : "memory");
}
__device__ __forceinline__ void fence_async() { asm volatile("fence.proxy.async.global;" ::: "memory"); }
__device__ __forceinline__ void fence_async_smem() { asm volatile("fence.proxy.async.shared::cta;" ::: "memory"); }
__device__ __forceinline__ void bar_sync(int id, int n) { asm volatile("bar.sync %0, %1;" ::"r"(id), "r"(n) : "memory"); }
__device__ __forceinline__ void bar_arrive(int id, int n) { asm volatile("bar.arrive %0, %1;" ::"r"(id), "r"(n) : "memory"); }
__device__ __forceinline__ void wg_fence() { asm volatile("wgmma.fence.sync.aligned;" ::: "memory"); }
__device__ __forceinline__ void wg_commit() { asm volatile("wgmma.commit_group.sync.aligned;" ::: "memory"); }
template <int N> __device__ __forceinline__ void wg_wait() { asm volatile("wgmma.wait_group.sync.aligned %0;" ::"n"(N) : "memory"); }
__device__ __forceinline__ uint64_t make_desc(uint32_t addr, uint32_t lbo, uint32_t sbo) {
  return (uint64_t)((addr & 0x3FFFF) >> 4) | ((uint64_t)(lbo >> 4) << 16) | ((uint64_t)(sbo >> 4) << 32) | (1ull << 62);
}
__device__ __forceinline__ uint32_t ld_relaxed(const uint32_t* p) {
  uint32_t v; asm volatile("ld.relaxed.gpu.global.u32 %0, [%1];" : "=r"(v) : "l"(p) : "memory"); return v;
}
__device__ __forceinline__ uint32_t ld_acquire(const uint32_t* p) {
  uint32_t v; asm volatile("ld.acquire.gpu.global.u32 %0, [%1];" : "=r"(v) : "l"(p) : "memory"); return v;
}
__device__ __forceinline__ uint4 ld_relaxed4(const uint32_t* p) {
  uint4 v; asm volatile("ld.relaxed.gpu.global.v4.u32 {%0,%1,%2,%3}, [%4];" : "=r"(v.x), "=r"(v.y), "=r"(v.z), "=r"(v.w) : "l"(p) : "memory"); return v;
}
__device__ __forceinline__ void st_relaxed(uint32_t* p, uint32_t v) {
  asm volatile("st.relaxed.gpu.global.u32 [%0], %1;" ::"l"(p), "r"(v) : "memory");
}
__device__ __forceinline__ void st_relaxed4(uint32_t* p, uint32_t a, uint32_t b, uint32_t c, uint32_t d) {
  asm volatile("st.relaxed.gpu.global.v4.u32 [%0], {%1,%2,%3,%4};" ::"l"(p), "r"(a), "r"(b), "r"(c), "r"(d) : "memory");
}
__device__ __forceinline__ void st_b128(uint32_t* p, uint32_t a, uint32_t b, uint32_t c, uint32_t d) {
  asm volatile("{ .reg .b64 u, v; .reg .b128 w; mov.b64 u, {%1, %2}; mov.b64 v, {%3, %4}; mov.b128 w, {u, v}; st.relaxed.gpu.global.b128 [%0], w; }"
               ::"l"(p), "r"(a), "r"(b), "r"(c), "r"(d) : "memory");
}
__device__ __forceinline__ uint4 ld_b128(const uint32_t* p) {
  uint4 r;
  asm volatile("{ .reg .b64 u, v; .reg .b128 w; ld.relaxed.gpu.global.b128 w, [%4]; mov.b128 {u, v}, w; mov.b64 {%0, %1}, u; mov.b64 {%2, %3}, v; }"
               : "=r"(r.x), "=r"(r.y), "=r"(r.z), "=r"(r.w) : "l"(p) : "memory");
  return r;
}
__device__ __forceinline__ void st_pairs(uint32_t* p, uint32_t a, uint32_t b, uint32_t tag) {
  asm volatile("{ .reg .b64 u, v; mov.b64 u, {%1, %3}; mov.b64 v, {%2, %3}; st.relaxed.gpu.global.v2.b64 [%0], {u, v}; }"
               ::"l"(p), "r"(a), "r"(b), "r"(tag) : "memory");
}
__device__ __forceinline__ uint4 ld_pairs(const uint32_t* p) {
  uint4 v;
  asm volatile("{ .reg .b64 u, v; ld.relaxed.gpu.global.v2.b64 {u, v}, [%4]; mov.b64 {%0, %1}, u; mov.b64 {%2, %3}, v; }"
               : "=r"(v.x), "=r"(v.y), "=r"(v.z), "=r"(v.w) : "l"(p) : "memory");
  return v;
}
__device__ __forceinline__ uint2 ld_pair(const uint32_t* p) {
  uint2 v;
  asm volatile("{ .reg .b64 u; ld.relaxed.gpu.global.b64 u, [%2]; mov.b64 {%0, %1}, u; }" : "=r"(v.x), "=r"(v.y) : "l"(p) : "memory");
  return v;
}
__device__ __forceinline__ void red_release(uint32_t* p, uint32_t v) {
  asm volatile("red.release.gpu.global.add.u32 [%0], %1;" ::"l"(p), "r"(v) : "memory");
}
__device__ __forceinline__ uint32_t ldg_nc1(const void* p) {
  uint32_t v;
  asm volatile("ld.global.nc.u32 %0, [%1];" : "=r"(v) : "l"(p));
  return v;
}
__device__ __forceinline__ uint4 ldg_nc4(const void* p) {
  uint4 v; asm volatile("ld.global.nc.L1::no_allocate.v4.u32 {%0,%1,%2,%3}, [%4];" : "=r"(v.x), "=r"(v.y), "=r"(v.z), "=r"(v.w) : "l"(p)); return v;
}
__device__ __forceinline__ uint4 ldg_stream4(const void* p) {
  uint4 v;
  asm volatile("ld.global.nc.L1::no_allocate.L2::cache_hint.v4.u32 {%0,%1,%2,%3}, [%4], %5;" : "=r"(v.x), "=r"(v.y), "=r"(v.z), "=r"(v.w) : "l"(p), "l"(l2_stream()));
  return v;
}
__device__ __forceinline__ void stg4(void* p, uint4 v) {
  asm volatile("st.global.v4.u32 [%0], {%1,%2,%3,%4};" ::"l"(p), "r"(v.x), "r"(v.y), "r"(v.z), "r"(v.w) : "memory");
}
__device__ __forceinline__ void wait_counter(const uint32_t* p, uint32_t target) {
  uint32_t n = 0;
  while (__any_sync(0xffffffffu, (int)(ld_acquire(p) - target) < 0)) { watchdog(n); }
}
__device__ __forceinline__ uint32_t tagf(float v, uint32_t tag) { return (__float_as_uint(v) & ~3u) | tag; }
__device__ __forceinline__ bool tag_ok(uint4 v, uint32_t tag) { return (((v.x ^ tag) | (v.y ^ tag) | (v.z ^ tag) | (v.w ^ tag)) & 3u) == 0; }
__device__ __forceinline__ float untag_sum(uint32_t a, uint32_t b) { return __uint_as_float(a & ~3u) + __uint_as_float(b & ~3u); }
__device__ __forceinline__ uint4 poll4(const uint32_t* p, uint32_t tag) {
  uint4 v = ld_relaxed4(p);
  uint32_t n = 0;
  while (!__all_sync(0xffffffffu, tag_ok(v, tag))) { v = ld_relaxed4(p); watchdog(n); }
  return v;
}
__device__ __forceinline__ float bf_lo(uint32_t v) { return __uint_as_float(v << 16); }
__device__ __forceinline__ float bf_hi(uint32_t v) { return __uint_as_float(v & 0xffff0000u); }
__device__ __forceinline__ uint32_t pack_bf(float lo, float hi) {
  uint32_t r; asm("cvt.rn.bf16x2.f32 %0, %1, %2;" : "=r"(r) : "f"(hi), "f"(lo)); return r;
}
__device__ __forceinline__ float rbf(float v) { return __uint_as_float(pack_bf(0.f, v) & 0xffff0000u); }
__device__ __forceinline__ uint32_t hmul2(uint32_t a, uint32_t b) {
  uint32_t r; asm("mul.rn.bf16x2 %0, %1, %2;" : "=r"(r) : "r"(a), "r"(b)); return r;
}
__device__ __forceinline__ uint32_t hadd2(uint32_t a, uint32_t b) {
  uint32_t r; asm("add.rn.bf16x2 %0, %1, %2;" : "=r"(r) : "r"(a), "r"(b)); return r;
}
__device__ __forceinline__ uint32_t hsub2(uint32_t a, uint32_t b) {
  uint32_t r; asm("sub.rn.bf16x2 %0, %1, %2;" : "=r"(r) : "r"(a), "r"(b)); return r;
}
__device__ __forceinline__ float rcp(float x) { float r; asm("rcp.approx.ftz.f32 %0, %1;" : "=f"(r) : "f"(x)); return r; }
__device__ __forceinline__ float ex2(float x) { float r; asm("ex2.approx.ftz.f32 %0, %1;" : "=f"(r) : "f"(x)); return r; }
__device__ __forceinline__ void stmatrix4(uint32_t addr, uint32_t a, uint32_t b, uint32_t c, uint32_t d) {
  asm volatile("stmatrix.sync.aligned.m8n8.x4.shared.b16 [%0], {%1,%2,%3,%4};" ::"r"(addr), "r"(a), "r"(b), "r"(c), "r"(d) : "memory");
}
__device__ __forceinline__ void ldmatrix4(uint32_t addr, uint32_t& a, uint32_t& b, uint32_t& c, uint32_t& d) {
  asm volatile("ldmatrix.sync.aligned.m8n8.x4.shared.b16 {%0,%1,%2,%3}, [%4];" : "=r"(a), "=r"(b), "=r"(c), "=r"(d) : "r"(addr) : "memory");
}
__device__ __forceinline__ void ldmatrix4t(uint32_t addr, uint32_t& a, uint32_t& b, uint32_t& c, uint32_t& d) {
  asm volatile("ldmatrix.sync.aligned.m8n8.x4.trans.shared.b16 {%0,%1,%2,%3}, [%4];" : "=r"(a), "=r"(b), "=r"(c), "=r"(d) : "r"(addr) : "memory");
}
__device__ __forceinline__ void mma16816(float (&d)[4], uint32_t a0, uint32_t a1, uint32_t a2, uint32_t a3, uint32_t b0, uint32_t b1) {
  asm volatile("mma.sync.aligned.m16n8k16.row.col.f32.bf16.bf16.f32 {%0,%1,%2,%3}, {%4,%5,%6,%7}, {%8,%9}, {%0,%1,%2,%3};"
               : "+f"(d[0]), "+f"(d[1]), "+f"(d[2]), "+f"(d[3]) : "r"(a0), "r"(a1), "r"(a2), "r"(a3), "r"(b0), "r"(b1));
}
__device__ __forceinline__ void sts1(uint32_t a, uint32_t v) { asm volatile("st.shared.u32 [%0], %1;" ::"r"(a), "r"(v) : "memory"); }
__device__ __forceinline__ uint4 lds4(uint32_t a) {
  uint4 v; asm volatile("ld.shared.v4.u32 {%0,%1,%2,%3}, [%4];" : "=r"(v.x), "=r"(v.y), "=r"(v.z), "=r"(v.w) : "r"(a) : "memory"); return v;
}
__device__ __forceinline__ uint2 lds2(uint32_t a) {
  uint2 v; asm volatile("ld.shared.v2.u32 {%0,%1}, [%2];" : "=r"(v.x), "=r"(v.y) : "r"(a) : "memory"); return v;
}
__device__ __forceinline__ uint32_t lds1(uint32_t a) {
  uint32_t v; asm volatile("ld.shared.u32 %0, [%1];" : "=r"(v) : "r"(a) : "memory"); return v;
}
__device__ __forceinline__ void sts2(uint32_t a, uint32_t x, uint32_t y) { asm volatile("st.shared.v2.u32 [%0], {%1,%2};" ::"r"(a), "r"(x), "r"(y) : "memory"); }
__device__ __forceinline__ void sts4(uint32_t a, uint4 v) {
  asm volatile("st.shared.v4.u32 [%0], {%1,%2,%3,%4};" ::"r"(a), "r"(v.x), "r"(v.y), "r"(v.z), "r"(v.w) : "memory");
}
__device__ __forceinline__ float silu_f(float v) { return __fdividef(v, 1.f + __expf(-v)); }
__device__ __forceinline__ uint32_t hfma2(uint32_t a, uint32_t b, uint32_t c) {
  uint32_t r; asm("fma.rn.bf16x2 %0, %1, %2, %3;" : "=r"(r) : "r"(a), "r"(b), "r"(c)); return r;
}
__device__ __forceinline__ void split_inv(float sd, uint32_t& ih, uint32_t& il) {
  const float inv = rcp(sd);
  ih = pack_bf(inv, inv);
  const float lo = inv - bf_lo(ih);
  il = pack_bf(lo, lo);
}
__device__ __forceinline__ uint32_t ln_norm(uint32_t x, uint32_t mean2, uint32_t ih, uint32_t il) {
  const uint32_t d = hsub2(x, mean2);
  return hfma2(d, ih, hmul2(d, il));
}
__device__ __forceinline__ uint32_t ln_mod(uint32_t x, uint32_t mean2, uint32_t ih, uint32_t il, uint32_t c1, uint32_t sh) {
  return hadd2(hmul2(ln_norm(x, mean2, ih, il), c1), sh);
}

#define R8(a, i) "+f"(a[i]), "+f"(a[i + 1]), "+f"(a[i + 2]), "+f"(a[i + 3]), "+f"(a[i + 4]), "+f"(a[i + 5]), "+f"(a[i + 6]), "+f"(a[i + 7])
#define D64 "{%0,%1,%2,%3,%4,%5,%6,%7,%8,%9,%10,%11,%12,%13,%14,%15,%16,%17,%18,%19,%20,%21,%22,%23,%24,%25,%26,%27,%28,%29,%30,%31," \
            "%32,%33,%34,%35,%36,%37,%38,%39,%40,%41,%42,%43,%44,%45,%46,%47,%48,%49,%50,%51,%52,%53,%54,%55,%56,%57,%58,%59,%60,%61,%62,%63}"
template <int TB>
__device__ __forceinline__ void mma_ss(float (&d)[64], uint64_t da, uint64_t db, int sc) {
  asm volatile("{\n.reg .pred p;\nsetp.ne.b32 p, %66, 0;\n"
               "wgmma.mma_async.sync.aligned.m64n128k16.f32.bf16.bf16 " D64 ", %64, %65, p, 1, 1, 0, %67;\n}"
               : R8(d, 0), R8(d, 8), R8(d, 16), R8(d, 24), R8(d, 32), R8(d, 40), R8(d, 48), R8(d, 56)
               : "l"(da), "l"(db), "r"(sc), "n"(TB));
}
template <int TB>
__device__ __forceinline__ void mma_rs(float (&d)[64], uint32_t a0, uint32_t a1, uint32_t a2, uint32_t a3, uint64_t db, int sc) {
  asm volatile("{\n.reg .pred p;\nsetp.ne.b32 p, %69, 0;\n"
               "wgmma.mma_async.sync.aligned.m64n128k16.f32.bf16.bf16 " D64 ", {%64,%65,%66,%67}, %68, p, 1, 1, %70;\n}"
               : R8(d, 0), R8(d, 8), R8(d, 16), R8(d, 24), R8(d, 32), R8(d, 40), R8(d, 48), R8(d, 56)
               : "r"(a0), "r"(a1), "r"(a2), "r"(a3), "l"(db), "r"(sc), "n"(TB));
}
#define D128 "{%0,%1,%2,%3,%4,%5,%6,%7,%8,%9,%10,%11,%12,%13,%14,%15,%16,%17,%18,%19,%20,%21,%22,%23,%24,%25,%26,%27,%28,%29,%30,%31," \
             "%32,%33,%34,%35,%36,%37,%38,%39,%40,%41,%42,%43,%44,%45,%46,%47,%48,%49,%50,%51,%52,%53,%54,%55,%56,%57,%58,%59,%60,%61,%62,%63," \
             "%64,%65,%66,%67,%68,%69,%70,%71,%72,%73,%74,%75,%76,%77,%78,%79,%80,%81,%82,%83,%84,%85,%86,%87,%88,%89,%90,%91,%92,%93,%94,%95," \
             "%96,%97,%98,%99,%100,%101,%102,%103,%104,%105,%106,%107,%108,%109,%110,%111,%112,%113,%114,%115,%116,%117,%118,%119,%120,%121,%122,%123,%124,%125,%126,%127}"
#define R128(d, e) R8(d, 0), R8(d, 8), R8(d, 16), R8(d, 24), R8(d, 32), R8(d, 40), R8(d, 48), R8(d, 56), \
                   R8(e, 0), R8(e, 8), R8(e, 16), R8(e, 24), R8(e, 32), R8(e, 40), R8(e, 48), R8(e, 56)
__device__ __forceinline__ void mma256_ss(float (&d)[64], float (&e)[64], uint64_t da, uint64_t db, int sc) {
  asm volatile("{\n.reg .pred p;\nsetp.ne.b32 p, %130, 0;\n"
               "wgmma.mma_async.sync.aligned.m64n256k16.f32.bf16.bf16 " D128 ", %128, %129, p, 1, 1, 0, 1;\n}"
               : R128(d, e) : "l"(da), "l"(db), "r"(sc));
}
__device__ __forceinline__ void mma256_rs(float (&d)[64], float (&e)[64], uint32_t a0, uint32_t a1, uint32_t a2, uint32_t a3, uint64_t db) {
  asm volatile("{\n.reg .pred p;\nsetp.ne.b32 p, 1, 0;\n"
               "wgmma.mma_async.sync.aligned.m64n256k16.f32.bf16.bf16 " D128 ", {%128,%129,%130,%131}, %132, p, 1, 1, 1;\n}"
               : R128(d, e) : "r"(a0), "r"(a1), "r"(a2), "r"(a3), "l"(db));
}
template <int N> __device__ __forceinline__ void keep(float (&a)[N]) {
#pragma unroll
  for (int i = 0; i < N; i++) asm volatile("" : "+f"(a[i])::"memory");
}
template <int N> __device__ __forceinline__ void keep(uint32_t (&a)[N]) {
#pragma unroll
  for (int i = 0; i < N; i++) asm volatile("" : "+r"(a[i])::"memory");
}

#define STAMP(idx) do {} while (0)
#define PROF(grp, cond, idx) do {} while (0)

constexpr float SCL2 = 1.4426950408889634f * 0.08838834764831845f;

__device__ __forceinline__ void pack_p(const float (&s)[64], uint32_t (&p)[32]) {
#pragma unroll
  for (int i = 0; i < 32; i++) p[i] = pack_bf(s[2 * i], s[2 * i + 1]);
}

__device__ __forceinline__ void issue_qk(float (&s)[64], uint32_t q0, uint32_t q1, uint32_t kslot) {
  const uint64_t db = make_desc(kslot, 16, 1024), da0 = make_desc(q0, 16, 1024), da1 = make_desc(q1, 16, 1024);
#pragma unroll
  for (int kk = 0; kk < 8; kk++) mma_ss<0>(s, (kk < 4 ? da0 : da1) + (kk & 3) * 2, db + (kk >> 2) * 1024 + (kk & 3) * 2, kk != 0);
}
__device__ __forceinline__ void issue_pv(float (&o)[64], uint32_t (&p)[32], uint32_t vslot, int acc) {
  uint64_t db = make_desc(vslot, 16384, 1024);
#pragma unroll
  for (int kk = 0; kk < 8; kk++)
    mma_rs<1>(o, p[4 * kk], p[4 * kk + 1], p[4 * kk + 2], p[4 * kk + 3], db + kk * 128, kk == 0 ? acc : 1);
}

template <int H>
__device__ __forceinline__ void store_chunk(const float (&a)[64], uint32_t addr) {
#pragma unroll
  for (int i = 8 * H; i < 8 * H + 8; i += 2)
    stmatrix4(addr ^ ((i & 7) << 4), pack_bf(a[4 * i], a[4 * i + 1]), pack_bf(a[4 * i + 2], a[4 * i + 3]),
              pack_bf(a[4 * i + 4], a[4 * i + 5]), pack_bf(a[4 * i + 6], a[4 * i + 7]));
}
template <int H>
__device__ __forceinline__ void store_chunk(const float (&a)[64], float i0, float i1, uint32_t addr) {
#pragma unroll
  for (int i = 8 * H; i < 8 * H + 8; i += 2)
    stmatrix4(addr ^ ((i & 7) << 4), pack_bf(a[4 * i] * i0, a[4 * i + 1] * i0), pack_bf(a[4 * i + 2] * i1, a[4 * i + 3] * i1),
              pack_bf(a[4 * i + 4] * i0, a[4 * i + 5] * i0), pack_bf(a[4 * i + 6] * i1, a[4 * i + 7] * i1));
}
__device__ __forceinline__ float inv_quad_sum(float l) {
  l += __shfl_xor_sync(0xffffffffu, l, 1);
  l += __shfl_xor_sync(0xffffffffu, l, 2);
  return rcp(l);
}

__device__ __forceinline__ void write_table(uint32_t table, bool ca, uint32_t t, const uint4& m0, const uint4& m1) {
  float c0 = untag_sum(m0.x, m1.x), c1 = untag_sum(m0.y, m1.y), c2 = untag_sum(m0.z, m1.z), c3 = untag_sum(m0.w, m1.w);
  if (ca) { c0 = 1.f + rbf(c0); c1 = 1.f + rbf(c1); c2 = 1.f + rbf(c2); c3 = 1.f + rbf(c3); }
  const uint32_t d = table + (t >> 2) * 64 + (t & 1) * 32 + (t & 2) * 2 + (ca ? 0 : 8);
  sts1(d, pack_bf(c0, c1));
  sts1(d + 16, pack_bf(c2, c3));
}

__device__ __forceinline__ void ln_scalars(float mean, float var, float& mb, float& sd) {
  mb = rbf(mean);
  float r; asm("sqrt.approx.ftz.f32 %0, %1;" : "=f"(r) : "f"(rbf(rbf(var) + 1e-5f)));
  sd = rbf(r);
}

__global__ void __cluster_dims__(2, 1, 1) __launch_bounds__(384, 1) fused_kernel(const __grid_constant__ Maps maps, const Ptrs P) {
  extern __shared__ __align__(1024) uint8_t smem_raw[];
  const uint32_t base = smem_u32(smem_raw);
  const int tid = threadIdx.x, lane = tid & 31;
  const int warp = __shfl_sync(0xffffffffu, tid >> 5, 0);
  int b = blockIdx.x;
  if (b < NMAIN) {
    const int p = b >> 1;
    const int grp = p < 4 ? 7 : (p < 36 ? (p + 2) & 7 : (p - 30) % 7), k = p < 4 ? 4 + p : (p < 36 ? (p - 4) >> 3 : 4 + (p - 36) / 7);
    b = grp << 4 | k << 1 | (b & 1);
  }
  PROF(31, tid == 0, 0);

  if (b >= NMAIN) {
    float* sc = reinterpret_cast<float*>(smem_raw);
    float* red = sc + DM;
    for (int k = tid; k < DM; k += 384) sc[k] = rbf(silu_f(__bfloat162float(P.c[k])));
    __syncthreads();
    if (tid < 256) {
      const int col = 2048 + (b - NMAIN) * 1024 + (tid & 127) * 8, r0 = (tid >> 7) * 512;
      float acc[8];
#pragma unroll
      for (int e = 0; e < 8; e++) acc[e] = 0.f;
#pragma unroll 1
      for (int r = r0; r < r0 + 512; r += HU) {
        uint4 w[HU];
#pragma unroll
        for (int u = 0; u < HU; u++) w[u] = ldg_stream4(P.w_mod + (size_t)(r + u) * NMOD + col);
#pragma unroll
        for (int u = 0; u < HU; u++) {
          float s = sc[r + u];
          acc[0] += s * bf_lo(w[u].x); acc[1] += s * bf_hi(w[u].x); acc[2] += s * bf_lo(w[u].y); acc[3] += s * bf_hi(w[u].y);
          acc[4] += s * bf_lo(w[u].z); acc[5] += s * bf_hi(w[u].z); acc[6] += s * bf_lo(w[u].w); acc[7] += s * bf_hi(w[u].w);
        }
      }
      if (tid >= 128) {
#pragma unroll
        for (int e = 0; e < 8; e++) red[(tid & 127) * 8 + e] = acc[e];
      }
      const uint32_t tag = ld_relaxed(&g_epoch) % 3 + 1;
      bar_sync(1, 256);
      if (tid < 128) {
        uint32_t o[8];
#pragma unroll
        for (int e = 0; e < 8; e++) o[e] = __float_as_uint(rbf(acc[e] + red[tid * 8 + e])) | tag;
        st_relaxed4(g_mod + col, o[0], o[1], o[2], o[3]);
        st_relaxed4(g_mod + col + 4, o[4], o[5], o[6], o[7]);
        const uint4 wr = ldg_nc4(P.w_r + tid * 8);
        const uint32_t wv[4] = {wr.x, wr.y, wr.z, wr.w};
        float dsum = 0.f;
#pragma unroll
        for (int e = 0; e < 8; e++) {
          const float m = bf_hi(o[e]);
          dsum += (b == NMAIN + 2 ? rbf(1.f + m) : m) * ((e & 1) ? bf_hi(wv[e >> 1]) : bf_lo(wv[e >> 1]));
        }
#pragma unroll
        for (int k = 16; k > 0; k >>= 1) dsum += __shfl_xor_sync(0xffffffffu, dsum, k);
        if (lane == 0) st_relaxed(g_mod + (b - NMAIN) * 4 + warp, tagf(dsum, tag));
      }
    }
    PROF(2, tid == 0, 1);
    return;
  }

  const int rank = b & 1;
  const int rb = ((b >> 4) << 1) | rank, cj = (b >> 1) & 7;
  const bool late = b & 4;
  const uint32_t bfull = base + OFF_BAR, bempty = bfull + NSLOT * 8;
  const uint32_t gfull = bempty + NSLOT * 8, gempty = gfull + 32;
  const uint32_t bar_ofull = gempty + 32;
  const uint32_t bar_ofree = bar_ofull + 32;
  const uint32_t bar_par = bar_ofree + 32;
  const uint32_t bar_mod = bar_par + 8;
  const uint32_t bar_pread = bar_mod + 8;
  const uint32_t bar_xres = bar_pread + 8;
  const uint32_t bar_ring = bar_xres + 8;
  const uint32_t bar_box = bar_ring + 24;
  const uint32_t bar_go = bar_box + 96;
  const uint32_t bar_go2 = bar_go + 16;
  const uint32_t bar_cnt = bar_go + 24;
  const uint32_t xfull = bar_go + 40, xempty = xfull + 32;
  const uint32_t bar_hw = xempty + 32, bar_hx = bar_hw + 8;
  const uint32_t bar_hpub = bar_hx + 16;
  const uint32_t bar_win = bar_hpub + 16;
  const uint32_t bar_rx = bar_win + 8;
  const uint32_t bar_sel = bar_rx + 8;
  const uint32_t bar_gate = bar_sel + 8;
  const uint32_t bar_rel = bar_gate + 8;
  const uint32_t bar_od = bar_rel + 8;
  const uint32_t bar_mod2 = bar_od + 8;
  const uint32_t bar_res = bar_go + 8;
  const uint32_t stage = base + OFF_STAGE, par = base + OFF_PAR;

  if (warp == 10 && elect_one()) prefetch_map(&maps.wm);
  if (warp == 8 && elect_one()) {
    for (int s = 0; s < NSLOT; s++) { mbar_init(bfull + s * 8, 1); mbar_init(bempty + s * 8, 16); }
    for (int s = 0; s < 4; s++) { mbar_init(gfull + s * 8, 1); mbar_init(gempty + s * 8, 16); mbar_init(xfull + s * 8, 1); mbar_init(xempty + s * 8, 8); mbar_init(bar_ofree + s * 8, 1); mbar_init(bar_ofull + s * 8, 128); }
    mbar_init(bar_par, 64); mbar_init(bar_mod, 256); mbar_init(bar_pread, 2); mbar_init(bar_xres, 1);
    mbar_init(bar_ring, 8); mbar_init(bar_ring + 8, 8); mbar_init(bar_ring + 16, 8);
    mbar_init(bar_go, 1); mbar_init(bar_go2, 1); mbar_init(bar_cnt, 1); mbar_init(bar_cnt + 8, 1); mbar_init(bar_hpub, 8); mbar_init(bar_hpub + 8, 8); mbar_init(bar_res, 1); mbar_init(bar_win, 1); mbar_init(bar_rx, 1); mbar_init(bar_sel, 64); mbar_init(bar_gate, 8); mbar_init(bar_rel, 8); mbar_init(bar_od, 1); mbar_init(bar_mod2, 64);
    for (int s = 0; s < 12; s++) mbar_init(bar_box + s * 8, 1);
    asm volatile("fence.mbarrier_init.release.cluster;" ::: "memory");
    prefetch_map(&maps.x); prefetch_map(&maps.wq); prefetch_map(&maps.k); prefetch_map(&maps.v);
  }
  if (warp == 9 && elect_one()) {
    mbar_init(bar_hw, 1); mbar_init(bar_hx, 1); mbar_init(bar_hx + 8, 1);
    asm volatile("fence.mbarrier_init.release.cluster;" ::: "memory");
    mbar_expect_tx(bar_hw, 32768);
    mbar_expect_tx(bar_hx, 16384);
    mbar_expect_tx(bar_hx + 8, 16384);
    const __nv_bfloat16* xs = P.x + (size_t)(rb * 128 + cj * 16) * DM;
    bulk_load(base + 2 * GST_BYTES, xs, 16384, bar_hx);
    if (!late) {
      tma2d(stage, &maps.wm, (b >> 1) * 32, rank * 512, bar_hw);
      tma2d(stage + 16384, &maps.wm, (b >> 1) * 32, rank * 512 + 256, bar_hw);
    }
    bulk_load(base + 3 * GST_BYTES, xs + 8 * DM, 16384, bar_hx + 8);
  }
  cluster_arrive();

  if (warp >= 8) {
    asm volatile("setmaxnreg.dec.sync.aligned.u32 40;");
    if (warp < 10) bar_arrive(1, 320);
    const uint32_t epoch = ld_relaxed(&g_epoch);
    cluster_wait();
    if (warp == 8) {
      const int kvrow = (cj >> 1) * SK + (SK - WIN);
      int wch = cj * 8 + rank * 2;
#pragma unroll 1
      for (int ps = 0; ps < 3; ps++) {
        const CUtensorMap* mw = ps == 2 ? &maps.wo : &maps.wq;
        const uint32_t xt = ps == 1 ? XT1 : XT2, wt = ps == 0 ? WT0 : (ps == 1 ? WT1 : WT2);
        const int nst = ps == 2 ? 32 : 16;
#pragma unroll 1
        for (int i = 0; i < nst; i++) {
          const uint32_t bf = gfull + (i & 3) * 8;
          const int kt = ps == 2 ? (((cj & 1) * 4 + ((i >> 1) & 3)) * 4 + (i >> 3)) * 2 + (i & 1) : (ps ? i : slice_of(i) + (b & 14)) & 15;
          const uint32_t wd = base + unit_of(wt, i & 3) + rank * UNIT, xd = base + unit_of(xt, i & 3);
          const uint8_t* xs = g_act + (uint32_t)(rb * 80 + (ps - 1) * 16 + kt) * UNIT;
          if (ps == 0 && i == HD) mbar_wait(bar_mod, 0);
          if (ps == 2 && (i & 7) == 0 && i != 8) mbar_wait(i ? bar_cnt + i - 16 : bar_ofree + 24, 0);
          if ((i & 7) == 0) fence_async();
          if (i == RES0) mbar_wait(bar_res, 0);
          mbar_wait(bf, ((i >> 2) & 1) ^ 1);
          if (elect_one()) {
            mbar_expect_tx(bf, ps ? GST_BYTES : 2 * UNIT);
            if (ps && i < 2) bulk_load_stream(xd, xs, UNIT, bf);
            mbar_arrive_pred(bar_go, i == GOST);
            mbar_arrive_pred(bar_go2, ps == 1 && i == PG0);
            mbar_arrive_pred(bar_od, ps && i == (ps == 1 ? ODS1 : ODS) + 1);
            if (i == RES0) mbar_expect_tx(bar_xres, 32768);
          }
          const int wk = (i == 31 ? kt ^ (rank * 32) : kt) * 64, wc = i == 31 ? cj * 2 : wch;
          const uint64_t xp = i == 31 ? l2_normal() : l2_stream();
          mbar_wait(ps && i < 4 ? bempty + i * 8 : gempty + (i & 3) * 8, ((i >> 2) & 1) ^ 1);
          if (elect_one()) {
            tma3d_mc<true>(wd, mw, 0, wk, wc, bf);
            if (ps && i > 2) bulk_load_stream(xd, xs, UNIT, bf, xp);
            if (i == RES0 || i == RES1) tma2d(base + OFF_RES + (i == RES1) * UNIT, &maps.x, cj * 128 + (i == RES1) * 64, rb * 128, bar_xres);
          }
          if (ps && i == 2) {
            mbar_wait(bar_ofree + (ps - 1) * 16, 0);
            if (elect_one()) bulk_load_stream(xd, xs, UNIT, bf);
          }
        }
        if (ps == 2) break;
        wch = ps ? ((wch >> 3) ^ rank) * 2 : wch + 4;
#pragma unroll 1
        for (int u = 0; u < 16; u++) {
          const bool isk = (u == 0) || ((u & 1) && u < 15), kept = (0x1680 >> u) & 1;
          const int blk = (0x472FAD84u >> (u * 2)) & 3;
          const uint32_t sl = base + unit_of(ps ? AT1 : AT0, u & 3) + rank * UNIT, bf = bfull + (u & 3) * 8;
          mbar_wait(bf, ((u >> 2) & 1) ^ 1);
          if (!kept && elect_one()) mbar_expect_tx(bf, SLOT_BYTES);
          mbar_wait(u < 4 ? gempty + ((u + 1) >> 1) * 8 : bempty + (u & 3) * 8, ((u >> 2) & 1) ^ 1);
          if (elect_one()) {
            if (kept) mbar_arrive(bf);
            else if (ps && (blk >= 2 || u > 8)) tma3d_mc<true>(sl, isk ? &maps.k : &maps.v, 0, kvrow + blk * 128, rank, bf);
            else tma3d_mc<false>(sl, isk ? &maps.k : &maps.v, 0, kvrow + blk * 128, rank, bf);
          }
        }
      }
      if (elect_one()) mbar_expect_tx(bar_rx, UNIT);
      mbar_wait(bar_rel, 0);
      if (elect_one()) {
        bulk_load_stream(base + UNIT, g_act + (uint32_t)(rb * 80 + 16 + 63 - (cj & 1) * 32) * UNIT, UNIT, bar_rx);
      }
      if (b < NFFN) {
#pragma unroll 1
        for (int u = 0; u < 12; u++) {
          const uint32_t dst = base + unit_of(u < 4 ? FT_G : (u < 8 ? FT_U : FT_D), u & 3);
          if (elect_one()) mbar_expect_tx(bar_box + u * 8, UNIT);
          if (u == 0 || u == 2 || u == 8) mbar_wait(bar_ring + (u == 8 ? 16 : u * 4), 0);
          const int fp = u < 8 ? FPACE0 : FPACE;
          if (u >= fp) mbar_wait(bar_box + (u - fp) * 8, 0);
          if (elect_one()) {
            if (u < 8) tma2d(dst, u < 4 ? &maps.wg : &maps.wu, b * 32, (u & 3) * 256, bar_box + u * 8);
            else tma3d(dst, &maps.wd, 0, b * 32, (u - 8) * 4, bar_box + u * 8);
          }
        }
      }
    } else if (warp == 9) {
      const uint32_t target = 8 * (epoch + 1);
      uint32_t hmask = 0;
#pragma unroll 1
      for (int i = 0; i < 16; i++) {
        if (i == HDX) mbar_wait(bar_mod, 0);
        const int kt = (2 * cj + slice_of(i)) & 15;
        const uint32_t need = i == 15 ? 0xffffu : 1u << kt;
        if (i >= NRS && (hmask & need) != need) {
          uint32_t n = 0;
          do { hmask = __ballot_sync(0xffffffffu, ld_acquire(&g_cnt_h[rb * 32 + (lane & 15)]) == epoch + 1); watchdog(n); } while ((hmask & need) != need);
          PROF(1, lane == 0 && i == NRS, 26);
          fence_async();
        }
        mbar_wait(xempty + (i & 3) * 8, ((i >> 2) & 1) ^ 1);
        if (elect_one()) {
          mbar_expect_tx(xfull + (i & 3) * 8, UNIT);
          if (i < NRS) tma2d(base + (i & 3) * GST_BYTES, &maps.x, kt * 64, rb * 128, xfull + (i & 3) * 8);
          else bulk_load_stream(base + (i & 3) * GST_BYTES, g_act + (uint32_t)(rb * 80 + kt) * UNIT, UNIT, xfull + (i & 3) * 8);
        }
      }
      prefetch_map(&maps.wo);
#pragma unroll 1
      for (int t = 0; t < 4; t++) {
        if (t & 1) mbar_wait(bar_od, t >> 1);
        const int ops = OPS >> (t & 1);
#pragma unroll 1
        for (int p = 0; p < 32768; p += ops) {
          const uint32_t w = p >> 14, c = (p >> 13) & 1, off = w * 8192 + (p & 8191);
          mbar_wait(bar_ofull + (t & 1) * 16 + w * 8, t >> 1);
          if (elect_one()) {
            bulk_store(g_act + (uint32_t)(rb * 80 + 16 + (cj * 4 + t) * 2 + c) * UNIT + off, base + unit_of(QT, 2 * t + c) + off, ops);
            asm volatile("cp.async.bulk.commit_group;" ::: "memory");
            asm volatile("cp.async.bulk.wait_group.read 0;" ::: "memory");
          }
        }
        if (elect_one()) {
          mbar_arrive(t < 3 ? bar_ofree + t * 8 : bar_res);
          asm volatile("cp.async.bulk.wait_group 0;" ::: "memory");
          fence_async();
          red_release(&g_cnt_o[((rb * 4 + t) * 2 + (cj >> 2)) * 32], 2);
        }
        if (t) {
          wait_counter(&g_cnt_o[(rb * 8 + 2 * t + (cj & 1)) * 32], target);
          if (t & 1) wait_counter(&g_cnt_o[(rb * 8 + (t == 1 ? cj & 1 : 7 - (cj & 1))) * 32], target);
          if (elect_one()) mbar_arrive(t == 1 ? bar_ofree + 24 : bar_cnt + t * 8 - 16);
        }
      }
      PROF(2, lane == 0, 27);
      const uint32_t tag = epoch % 3 + 1;
      const uint32_t* inbox = g_cand + (b >> 4) % CR * 512 + (lane & 15) * CS;
      mbar_wait(bar_ring + 16, 0);
      uint32_t c0 = ld_relaxed(inbox), n = 0;
#define CAND_STEP(cv)                                                                                        \
      {                                                                                                      \
        const bool valid = (cv & 3u) == tag, all = __all_sync(0xffffffffu, valid);                           \
        const uint32_t best = __reduce_max_sync(0xffffffffu, valid ? cv : 0u);                               \
        const uint32_t blk = __ffs(__ballot_sync(0xffffffffu, cv == best)) - 1;                              \
        if (best) sts2(par + PAR_CONST + 56, best, (blk << 7 | (~best >> 2 & 127)) | (all ? 0x1800 : 0x800)); \
        if (all) break;                                                                                      \
        cv = ld_relaxed(inbox);                                                                              \
      }
      while (true) { CAND_STEP(c0) watchdog(n); }
    } else {
      const int t2 = tid - 320;
      if (late && warp == 10) {
        mbar_wait(bar_hx, 0);
        if (elect_one()) {
          tma2d(stage, &maps.wm, (b >> 1) * 32, rank * 512, bar_hw);
          tma2d(stage + 16384, &maps.wm, (b >> 1) * 32, rank * 512 + 256, bar_hw);
        }
      }
      {
        const uint32_t tag = epoch % 3 + 1;
        mbar_wait(bar_hx + 8, 0);
        mbar_wait(bar_hw, 0);
        __nanosleep(late ? OSL2 : OSL);
        {
          const uint32_t t7 = (warp & 1) * 64 + (lane >> 4) * 32 + 16 + (lane & 15);
          const uint32_t* pm = g_modp + ((cj * 128 + t7 * 4) & (DM - 1));
          uint4 m0, m1, m2, m3;
          uint32_t n = 0;
          do {
            m0 = ld_relaxed4(pm); m1 = ld_relaxed4(pm + 2 * DM); m2 = ld_relaxed4(pm + DM); m3 = ld_relaxed4(pm + 3 * DM);
            watchdog(n);
          } while (!__all_sync(0xffffffffu, tag_ok(m0, tag) && tag_ok(m1, tag) && tag_ok(m2, tag) && tag_ok(m3, tag)));
          write_table(par, false, t7, m0, m1);
          write_table(par, true, t7, m2, m3);
          mbar_arrive(bar_mod2);
        }
      }
      mbar_wait(bar_hpub + (warp & 1) * 8, 0);
      PROF(1, t2 == 0, 24);
#pragma unroll 1
      for (int c = 0; c < 8; c++) {
        const uint32_t off = (warp & 1) * UNIT + c * 2048 + lane * 16;
        uint8_t* dst = g_act + (uint32_t)(rb * 80 + cj * 2) * UNIT + off;
        const uint4 v0 = lds4(stage + off), v1 = lds4(stage + off + 512), v2 = lds4(stage + off + 1024), v3 = lds4(stage + off + 1536);
        stg4(dst, v0); stg4(dst + 512, v1); stg4(dst + 1024, v2); stg4(dst + 1536, v3);
      }
      __syncwarp();
      PROF(1, t2 == 0, 15);
      if (lane == 0) {
        mbar_arrive(bar_pread);
        red_release(&g_cnt_h[rb * 32 + cj * 2 + (warp & 1)], 1);
        PROF(1, t2 == 0, 25);
        prefetch_map(&maps.wg); prefetch_map(&maps.wu); prefetch_map(&maps.wd); prefetch_map(&maps.out);
      }
      __syncwarp();
      if (b < NFFN) {
        mbar_wait(bar_go2, 0);
        const __nv_bfloat16* pg = ((b & 1) ? P.w_up : P.w_gate) + (b >> 1) * 64 + (size_t)t2 * FF;
        const __nv_bfloat16* pd = P.w_down + (size_t)b * 32768 + t2 * 64;
        PROF(2, t2 == 0, 13);
#pragma unroll 1
        for (int i = 0; i < WN; i += WB) {
          uint32_t v[WB];
#pragma unroll
          for (int u = 0; u < WB; u++) {
            const int k = i + u;
            asm volatile("ld.global.cg.L2::128B.u32 %0, [%1];" : "=r"(v[u]) : "l"(k < 16 ? pg + (size_t)k * 64 * FF : pd + (k - 16) * 4096));
          }
#pragma unroll
          for (int u = 1; u < WB; u++) v[0] ^= v[u];
          sts1(par + PAR_SINK + t2 * 4, v[0]);
        }
        PROF(2, t2 == 0, 14);
      }
      const uint32_t tag = epoch % 3 + 1;
      mbar_wait(bar_go, 0);
      bar_sync(4, 64);
      if (warp == 10) {
        const uint32_t* src = g_mod + 2 * DM + cj * 128 + lane * 4;
        const uint2 wr = *reinterpret_cast<const uint2*>(P.w_r + cj * 128 + lane * 4);
        uint4 vga, vsb, vcb, vgb;
        uint32_t n = 0;
        do {
          vga = ld_relaxed4(src); vsb = ld_relaxed4(src + DM); vcb = ld_relaxed4(src + 2 * DM); vgb = ld_relaxed4(src + 3 * DM);
          watchdog(n);
        } while (!__all_sync(0xffffffffu, tag_ok(vga, tag) && tag_ok(vsb, tag) && tag_ok(vcb, tag) && tag_ok(vgb, tag)));
        const float c0 = rbf(1.f + bf_hi(vcb.x)), c1 = rbf(1.f + bf_hi(vcb.y)), c2 = rbf(1.f + bf_hi(vcb.z)), c3 = rbf(1.f + bf_hi(vcb.w));
        const float a0 = c0 * bf_lo(wr.x), a1 = c1 * bf_hi(wr.x), a2 = c2 * bf_lo(wr.y), a3 = c3 * bf_hi(wr.y);
        const uint32_t h0 = pack_bf(a0, a1), h1 = pack_bf(a2, a3);
        const uint32_t t1 = par + PAR_T1 + (lane >> 2) * 64 + (lane & 1) * 32 + (lane & 2) * 2;
        sts1(t1, h0); sts1(t1 + 8, pack_bf(a0 - bf_lo(h0), a1 - bf_hi(h0)));
        sts1(t1 + 16, h1); sts1(t1 + 24, pack_bf(a2 - bf_lo(h1), a3 - bf_hi(h1)));
        const uint32_t tg = par + PAR_SINK + (lane >> 3) * 64 + (lane & 1) * 32 + (lane & 6) * 2;
        sts1(tg, __byte_perm(vga.x, vga.y, 0x7632)); sts1(tg + 16, __byte_perm(vga.z, vga.w, 0x7632));
        sts4(par + PAR_T2 + lane * 32, make_uint4(pack_bf(c0, c1), __byte_perm(vsb.x, vsb.y, 0x7632), __byte_perm(vgb.x, vgb.y, 0x7632), __byte_perm(vga.x, vga.y, 0x7632)));
        sts4(par + PAR_T2 + lane * 32 + 16, make_uint4(pack_bf(c2, c3), __byte_perm(vsb.z, vsb.w, 0x7632), __byte_perm(vgb.z, vgb.w, 0x7632), __byte_perm(vga.z, vga.w, 0x7632)));
      } else {
        const uint4 g = poll4((lane & 8) ? g_mod + 8 - (lane & 1) * 4 : g_mod + 5 * DM + (b >> 4) * 128 + (lane & 7) * 16 + (b & 12), tag);
        sts1(par + PAR_CONST + 60, 0);
        if (lane < 8) sts1(par + PAR_CONST + 16 + lane * 4, (b & 2) ? ((b & 1) ? g.w : g.z) : ((b & 1) ? g.y : g.x));
        else if (lane < 10) sts2(par + PAR_CONST + (lane - 8) * 8, __float_as_uint(untag_sum(g.x, g.y) + untag_sum(g.z, g.w)), epoch);
      }
      __syncwarp();
#pragma unroll 1
      for (int q = 0; q < 32; q++) {
        st_b128(g_xch + ((size_t)b * 8 * 256 + q * 64 + t2) * 4, (epoch & 1) << 16, 0, 0, 0);
        __nanosleep(RSL);
      }
      for (int q = 0; q < 2; q++) st_relaxed4(g_stats + (((rb * 8 + q * 4 + (t2 >> 4)) * 8 + cj) * 16 + (t2 & 15)) * 4, 0, 0, 0, 0);
      if (b < NFFN)
        for (int q = 0; q < 2; q++) st_relaxed4(ypart_slot(b, q * 64 + t2), 0, 0, 0, 0);
      st_relaxed4(g_row + rb * 2 * DM + (t2 >> 5) * DM + cj * 128 + (t2 & 31) * 4, 0, 0, 0, 0);
      __threadfence();
      mbar_arrive(bar_par);
      mbar_wait(bar_gate, 0);
      uint32_t have = 0, n = 0;
      while (true) {
        const uint32_t st = lds1(par + PAR_CONST + 60) >> 7;
        if ((st & 31) != have) {
          const uint32_t* hsrc = g_row + (st & 15) * 2 * DM + t2 * 4;
          uint4 hv[4];
          bool ok = true;
#pragma unroll
          for (int i = 0; i < 4; i++) hv[i] = ld_pairs(hsrc + i * 256);
#pragma unroll
          for (int i = 0; i < 4; i++) {
            sts2(base + ((FT_G >> i * 4) & 15) * UNIT + (warp & 1) * 8192 + 256 + lane * 8, hv[i].x, hv[i].z);
            ok = ok && hv[i].y == tag && hv[i].w == tag;
          }
          have = __all_sync(0xffffffffu, ok) ? st & 31 : 0;
        }
        if ((st ^ have) == 32) break;
        watchdog(n);
      }
      mbar_arrive(bar_sel);
    }
    __syncwarp();
    cluster_arrive();
    {
      const uint32_t tag = epoch % 3 + 1, t3 = tid - 256;
      mbar_wait(bar_win, 0);
      uint2 win = lds2(par + PAR_CONST + 56);
      win.y &= 0x7ff;
      const uint32_t* fsrc = g_row + (win.y >> 7) * 2 * DM + (b >> 4) * 128 + (t3 & 7) * 16 + (b & 6) * 2 + ((b >> 2) & 2);
      const uint32_t* ysrc = ypart_slot(min(t3, NFFN - 1), b);
      uint2 fh = ld_pair(fsrc), fx = ld_pair(fsrc + DM);
      uint4 ya = ld_b128(ysrc);
      const float rwin = __uint_as_float(((int)win.x < 0 ? win.x & 0x7fffffffu : ~win.x) & ~0x1ffu);
      const float rs = rbf(rcp(1.f + __expf(-rbf(rwin))));
      uint32_t n = 0;
      while (__any_sync(0xffffffffu, fh.y != tag || fx.y != tag)) { fh = ld_pair(fsrc); fx = ld_pair(fsrc + DM); watchdog(n); }
      while (true) {
        const bool miss = ((ya.x & 1) | (ya.y & 1) << 1) != tag;
        if (!__any_sync(0xffffffffu, miss)) break;
        if (miss) ya = ld_b128(ysrc);
        watchdog(n);
      }
      PROF(8, t3 == 0, 5);
      float y[8] = {bf_lo(ya.x & ~1u), bf_hi(ya.x), bf_lo(ya.y & ~1u), bf_hi(ya.y), bf_lo(ya.z), bf_hi(ya.z), bf_lo(ya.w), bf_hi(ya.w)};
#pragma unroll
      for (int h = 4; h > 0; h >>= 1) {
        const bool up = lane & (h * 2);
#pragma unroll
        for (int e = 0; e < h; e++) y[e] = (up ? y[e + h] : y[e]) + __shfl_xor_sync(0xffffffffu, up ? y[e] : y[e + h], h * 2);
      }
      y[0] += __shfl_xor_sync(0xffffffffu, y[0], 1);
      if (!(lane & 1)) sts1(par + PAR_RED + 64 + t3 * 2, __float_as_uint(y[0]));
      bar_sync(4, 128);
      if (t3 < 8) {
        float y0 = 0.f;
#pragma unroll
        for (int w7 = 0; w7 < 7; w7++) y0 += __uint_as_float(lds1(par + PAR_RED + 64 + w7 * 32 + t3 * 4));
        const uint32_t gv = lds1(par + PAR_CONST + 16 + t3 * 4);
        const uint32_t upd = hmul2(pack_bf(y0, y0), pack_bf(rs, rs));
        const uint32_t r = hadd2(fx.x, hmul2(__byte_perm(gv, gv, 0x3232), hadd2(fh.x, upd)));
        reinterpret_cast<uint16_t*>(P.out)[(size_t)win.y * DM + (b >> 4) * 128 + t3 * 16 + (b & 15)] = (b & 1) ? r >> 16 : r;
        if (b == 0 && t3 == 0) st_relaxed(&g_epoch, epoch + 1);
      }
      PROF(31, t3 == 0, 36);
    }
    cluster_wait();
  } else {
    const int wg = warp >> 2;

    uint32_t tag;
    auto gemv = [&]() {
      const uint32_t l = fresh_lane(), fr = (l & 7) + (l >> 4) * 8, tq = l & 3, row = base + 2 * GST_BYTES + warp * 2048;
      const uint32_t wa = stage + warp * 4096 + fr * 64 + ((((l >> 3) & 1) ^ ((fr >> 1) & 3)) << 4);
      uint32_t sc[8];
#pragma unroll
      for (int k = 0; k < 8; k++) sc[k] = lds1(row + 128 + k * 16 + tq * 4);
      float d0[4] = {0.f, 0.f, 0.f, 0.f}, d1[4] = {0.f, 0.f, 0.f, 0.f};
      mbar_wait(bar_hw, 0);
#pragma unroll
      for (int ks = 0; ks < 4; ks++) {
        uint32_t w[8];
        ldmatrix4t(wa + ks * 1024, w[0], w[1], w[2], w[3]);
        ldmatrix4t((wa ^ 32) + ks * 1024, w[4], w[5], w[6], w[7]);
        mma16816(d0, w[0], w[1], w[2], w[3], sc[2 * ks], sc[2 * ks + 1]);
        mma16816(d1, w[4], w[5], w[6], w[7], sc[2 * ks], sc[2 * ks + 1]);
      }
      sts1(row + (tq * 8 + (l >> 2)) * 4, __float_as_uint((tq & 2) ? ((tq & 1) ? d1[2] : d1[0]) : ((tq & 1) ? d0[2] : d0[0])));
      bar_sync(1, 256);
      if (warp == 0) {
        float s = 0.f;
#pragma unroll
        for (int w8 = 0; w8 < 8; w8++) s += __uint_as_float(lds1(row + w8 * 2048 + l * 4));
        st_relaxed(g_modp + rank * 2 * DM + (b >> 1) * 32 + l, (__float_as_uint(s) & ~3u) | tag);
      }
      PROF(1, tid == 0, 3);
    };
    {
      uint32_t* const pmod = g_modp + rank * 2 * DM + (b >> 1) * 32 + lane;
      uint32_t* const pln = g_ln1 + (rb * 128 + cj * 16 + warp) * 4;
      const uint32_t cv = ldg_nc1(P.c + rank * 512 + tid * 2);
      const uint32_t epoch = ld_relaxed(&g_epoch);
      if (warp == 0) st_relaxed(pmod, 0);
      if (lane == 0) { st_b128(pln, 0, 0, 0, 0); st_b128(pln + 32, 0, 0, 0, 0); }
      asm volatile("setmaxnreg.inc.sync.aligned.u32 232;");
      bar_sync(1, 320);
      tag = epoch % 3 + 1;
#pragma unroll
      for (int part = 0; part < 3; part++) {
        if (!(part & 1)) {
          const uint32_t xa = base + (2 + part / 2) * GST_BYTES + warp * 2048 + lane * 16;
          mbar_wait(bar_hx + part * 4, 0);
          float s0 = 0.f, s1 = 0.f, q0 = 0.f, q1 = 0.f;
#pragma unroll
          for (int q = 0; q < 4; q++) {
            const uint4 xv = lds4(xa + q * 512);
            const uint32_t u[4] = {xv.x, xv.y, xv.z, xv.w};
#pragma unroll
            for (int e = 0; e < 4; e++) { const float lo = bf_lo(u[e]), hi = bf_hi(u[e]); s0 += lo; s1 += hi; q0 += lo * lo; q1 += hi * hi; }
          }
          s0 += s1; q0 += q1;
#pragma unroll
          for (int o = 16; o > 0; o >>= 1) { s0 += __shfl_xor_sync(0xffffffffu, s0, o); q0 += __shfl_xor_sync(0xffffffffu, q0, o); }
          const float mean = s0 * (1.f / DM);
          float mb, sd;
          ln_scalars(mean, fmaxf(q0 * (1.f / DM) - mean * mean, 0.f), mb, sd);
          uint32_t ih, il;
          split_inv(sd, ih, il);
          if (lane == 0) st_b128(pln + part * 16, pack_bf(mb, mb), ih, il, tag);
          PROF(1, tid == 0 && part == 2, 4);
        } else {
          __syncwarp();
          sts1(base + 2 * GST_BYTES + warp * 2048 + 128 + lane * 4, pack_bf(silu_f(bf_lo(cv)), silu_f(bf_hi(cv))));
          __syncwarp();
          if (!late) gemv();
        }
      }
      cluster_wait();
      if (wg == 1) bar_arrive(2, 256);
    }

    const uint32_t rempty = lane < 2 ? mapa(bempty, lane & 1) : 0;
    constexpr uint32_t GE = NSLOT * 8 + 32;
    float o[64], s[64];
#pragma unroll 1
    for (int ps = 0; ps < 3; ps++) {
      {
        const uint32_t xt = ps == 1 ? XT1 : XT2, wt = ps == 1 ? WT1 : WT2;
        const int nst = ps == 2 ? 28 : 14;
        if (ps == 0) {
          float ga[64], gb[64];
#pragma unroll
          for (int i = 0; i < 64; i++) { ga[i] = 0.f; gb[i] = 0.f; }
          uint32_t a[2][16];
          const uint32_t l = fresh_lane();
          uint32_t fa[4];
#pragma unroll
          for (int kk = 0; kk < 4; kk++) fa[kk] = (base + wg * 8192 + frag_offset(warp)) ^ (kk * 32);
          const uint32_t mt = par + (l & 3) * 16;
          auto fetch = [&](int i, uint32_t (&f)[16], uint32_t z) {
            mbar_wait(xfull + (i & 3) * 8, i >> 2);
#pragma unroll
            for (int kk = 0; kk < 4; kk++) ldmatrix4(fa[kk] + (i & 3) * GST_BYTES + z, f[4 * kk], f[4 * kk + 1], f[4 * kk + 2], f[4 * kk + 3]);
          };
          const bool oddw = warp & 2;
          uint4 r0, r1;
          {
            const uint32_t t7 = (warp & 1) * 64 + (l >> 4) * 32 + (l & 15);
            const uint32_t* pm = g_modp + wg * DM + ((cj * 128 + t7 * 4) & (DM - 1));
            const uint32_t* pr = g_ln1 + (rb * 128 + warp * 16 + (l >> 2)) * 4;
            uint4 m0 = make_uint4(tag, tag, tag, tag), m1 = m0;
            if (GL == 0 && late) gemv();
            if (GL == 2) { fetch(0, a[0], 0); fetch(1, a[1], 0); }
            mbar_wait(bar_hw, 0);
            if (!oddw) { m0 = ld_relaxed4(pm); m1 = ld_relaxed4(pm + 2 * DM); }
            r0 = ld_b128(pr); r1 = ld_b128(pr + 32);
            if (GL && late) gemv();
            if (GL != 2) { fetch(0, a[0], 0); fetch(1, a[1], 0); }
            uint32_t n = 0;
            bool written = false;
#pragma unroll 1
            while (true) {
              uint32_t miss;
              asm volatile("{ .reg .pred p0, p1, p2, p3; .reg .b32 t, u;\n"
                           "lop3.b32 t, %1, %2, %19, 0x7e; lop3.b32 u, %3, %4, %19, 0x7e; or.b32 t, t, u; and.b32 t, t, 3; setp.ne.u32 p0, t, 0;\n"
                           "lop3.b32 t, %5, %6, %19, 0x7e; lop3.b32 u, %7, %8, %19, 0x7e; or.b32 t, t, u; and.b32 t, t, 3; setp.ne.u32 p1, t, 0;\n"
                           "setp.ne.u32 p2, %12, %19; setp.ne.u32 p3, %16, %19;\n"
                           "@p0 ld.relaxed.gpu.global.v4.u32 {%1, %2, %3, %4}, [%17];\n"
                           "@p1 ld.relaxed.gpu.global.v4.u32 {%5, %6, %7, %8}, [%17 + 8192];\n"
                           "@p2 ld.relaxed.gpu.global.v4.u32 {%9, %10, %11, %12}, [%18];\n"
                           "@p3 ld.relaxed.gpu.global.v4.u32 {%13, %14, %15, %16}, [%18 + 128];\n"
                           "or.pred p0, p0, p1; or.pred p2, p2, p3; vote.sync.any.pred p0, p0, 0xffffffff; vote.sync.any.pred p2, p2, 0xffffffff;\n"
                           "selp.u32 t, 1, 0, p0; selp.u32 u, 2, 0, p2; or.b32 %0, t, u; }"
                           : "=r"(miss), "+r"(m0.x), "+r"(m0.y), "+r"(m0.z), "+r"(m0.w), "+r"(m1.x), "+r"(m1.y), "+r"(m1.z), "+r"(m1.w),
                             "+r"(r0.x), "+r"(r0.y), "+r"(r0.z), "+r"(r0.w), "+r"(r1.x), "+r"(r1.y), "+r"(r1.z), "+r"(r1.w)
                           : "l"(pm), "l"(pr), "r"(tag) : "memory");
              if (!(miss & 1) && !written) {
                written = true;
                if (!oddw) write_table(par, wg, t7, m0, m1);
                mbar_arrive(bar_mod);
              }
              if (!miss) break;
              watchdog(n);
            }
          }
          const uint32_t zero = r0.w ^ tag;
          auto normalize = [&](uint32_t (&f)[16]) {
#pragma unroll
            for (int k = 0; k < 16; k += 2) { f[k] = ln_norm(f[k], r0.x, r0.y, r0.z); f[k + 1] = ln_norm(f[k + 1], r1.x, r1.y, r1.z); }
          };
          auto modulate = [&](int i, uint32_t (&f)[16]) {
#pragma unroll
            for (int kk = 0; kk < 4; kk++) {
              const uint4 m = lds4(mt + slice_of(i) * 256 + kk * 64);
              f[4 * kk] = hfma2(f[4 * kk], m.x, m.z); f[4 * kk + 1] = hfma2(f[4 * kk + 1], m.x, m.z);
              f[4 * kk + 2] = hfma2(f[4 * kk + 2], m.y, m.w); f[4 * kk + 3] = hfma2(f[4 * kk + 3], m.y, m.w);
            }
            keep(f);
            mbar_arrive_pred(xempty + (i & 3) * 8, l == 0);
          };
          auto publish = [&](int u, uint32_t (&f)[16]) {
#pragma unroll
            for (int kk = 0; kk < 4; kk++) stmatrix4(fa[kk] + OFF_STAGE + u * UNIT, f[4 * kk], f[4 * kk + 1], f[4 * kk + 2], f[4 * kk + 3]);
            __syncwarp();
            mbar_arrive_pred(bar_hpub + u * 8, l == 0);
          };
          auto multiply = [&](int i, uint32_t (&f)[16]) {
            mbar_wait(gfull + (i & 3) * 8, i >> 2);
            const uint64_t db = make_desc(base + (i & 3) * GST_BYTES + UNIT, 8192, 1024);
            wg_fence();
#pragma unroll
            for (int kk = 0; kk < 4; kk++) mma256_rs(ga, gb, f[4 * kk], f[4 * kk + 1], f[4 * kk + 2], f[4 * kk + 3], db + kk * 128);
            wg_commit();
          };
          auto next = [&](int i, uint32_t (&f)[16]) {
            wg_wait<1>();
            mbar_arrive_cl(rempty, GE + ((i + 2) & 3) * 8);
            uint32_t z = zero;
#pragma unroll
            for (int k = 0; k < 16; k += 2) asm volatile("lop3.b32 %0, %1, %2, %0, 0xA8;" : "+r"(z) : "r"(f[k]), "r"(f[k + 1]));
            fetch(i, f, z);
            normalize(f);
            if (i == 2) { keep(f); mbar_wait(bar_mod2, 0); }
            modulate(i, f); multiply(i, f);
          };
          normalize(a[0]);
          keep(a[0]); keep(a[1]);
          mbar_wait(bar_mod, 0);
          PROF(1, tid == 0, 2);
          modulate(0, a[0]); multiply(0, a[0]); publish(0, a[0]);
          keep(a[1]);
          normalize(a[1]);
          modulate(1, a[1]); multiply(1, a[1]);
#pragma unroll 1
          for (int i = 2; i < NRS; i += 2) {
            next(i, a[0]);
            if (i == 2) publish(1, a[0]);
            next(i + 1, a[1]);
          }
          wg_wait<1>();
          mbar_arrive_cl(rempty, GE + ((NRS + 2) & 3) * 8);
#pragma unroll 1
          for (int i = NRS; i < 14; i++) {
            mbar_wait(xfull + (i & 3) * 8, (i >> 2) & 1);
            mbar_wait(gfull + (i & 3) * 8, (i >> 2) & 1);
            const uint32_t xa = base + (i & 3) * GST_BYTES;
            const uint64_t da = make_desc(xa + wg * 8192, 16, 1024), db = make_desc(xa + UNIT, 8192, 1024);
            if (i == 13) bar_sync(2 + wg, 256);
            wg_fence();
#pragma unroll
            for (int kk = 0; kk < 4; kk++) mma256_ss(ga, gb, da + kk * 2, db + kk * 128, 1);
            wg_commit();
            if (i == 13) bar_arrive(3 - wg, 256);
            wg_wait<1>();
            uint32_t z = zero;
#pragma unroll
            for (int k = 0; k < 16; k += 2) asm volatile("lop3.b32 %0, %1, %2, %0, 0xA8;" : "+r"(z) : "r"(a[1][k]), "r"(a[1][k + 1]));
            mbar_arrive_cl(rempty, GE + ((i + 3) & 3) * 8 + z);
            mbar_arrive_pred(xempty + ((i + 3) & 3) * 8, l == 0 && i != NRS);
          }
          mbar_wait(xfull + 16, 1);
          wg_wait<0>();
          keep(ga); keep(gb);
#pragma unroll
          for (int i = 0; i < 64; i++) {
            asm volatile("mov.b32 %0, %1;" : "=f"(s[i]) : "f"(ga[i]));
            asm volatile("mov.b32 %0, %1;" : "=f"(o[i]) : "f"(gb[i]));
          }
        } else {
          float ga[64], gb[64];
#pragma unroll
          for (int i = 0; i < 64; i++) {
            asm volatile("mov.b32 %0, %1;" : "=f"(ga[i]) : "f"(s[i]));
            asm volatile("mov.b32 %0, %1;" : "=f"(gb[i]) : "f"(o[i]));
          }
#pragma unroll 1
          for (int i = 0; i < nst; i++) {
            mbar_wait(gfull + (i & 3) * 8, (i >> 2) & 1);
            const uint64_t da = make_desc(base + unit_of(xt, i & 3) + wg * 8192, 16, 1024), db = make_desc(base + unit_of(wt, i & 3), 8192, 1024);
            if (i == nst - 1) bar_sync(2 + wg, 256);
            wg_fence();
#pragma unroll
            for (int kk = 0; kk < 4; kk++) mma256_ss(ga, gb, da + kk * 2, db + kk * 128, kk ? 1 : i);
            wg_commit();
            if (i == nst - 1) bar_arrive(3 - wg, 256);
            wg_wait<1>();
            mbar_arrive_cl(rempty, GE + ((i + 3) & 3) * 8, i != 0);
            PROF(4, tid == 0 && (i & 3) == 0, 40 + (ps - 1) * 4 + i / 4);
          }
          wg_wait<0>();
          keep(ga); keep(gb);
#pragma unroll
          for (int i = 0; i < 64; i++) {
            asm volatile("mov.b32 %0, %1;" : "=f"(s[i]) : "f"(ga[i]));
            asm volatile("mov.b32 %0, %1;" : "=f"(o[i]) : "f"(gb[i]));
          }
        }
        mbar_arrive_cl(rempty, GE + (ps == 2 ? 24 : 8));
        if (ps == 2) break;
      }
      const uint32_t qw = base + wg * 8192, qt = QT >> (16 * ps), at = ps ? AT1 : AT0;
      {
        const uint32_t wt = ps ? WT1 : WT0;
        const uint64_t da0 = make_desc(qw + unit_of(qt, 2), 16, 1024), da1 = make_desc(qw + unit_of(qt, 3), 16, 1024);
        const uint64_t db0 = make_desc(base + unit_of(wt, 2), 8192, 1024), db1 = make_desc(base + unit_of(wt, 3), 8192, 1024);
        mbar_wait(gfull + 16, 1);
        bar_sync(2 + wg, 256);
        wg_fence();
#pragma unroll
        for (int kk = 0; kk < 4; kk++) mma_ss<1>(s, da0 + kk * 2, db0 + kk * 128, 1);
        wg_commit();
        mbar_wait(xfull + 24, 1);
        mbar_wait(gfull + 24, 1);
        wg_fence();
#pragma unroll
        for (int kk = 0; kk < 4; kk++) mma_ss<1>(s, da1 + kk * 2, db1 + kk * 128, 1);
        wg_commit();
        bar_arrive(3 - wg, 256);
        mbar_wait(ps == 0 ? bar_pread : bar_ofree + 8, 0);
        wg_wait<0>();
        keep(s);
        PROF(2, tid == 0, 8 + ps * 8);
        uint32_t q[32];
        pack_p(s, q);
#pragma unroll
        for (int i = 0; i < 4; i++) stmatrix4((qw + unit_of(qt, 0) + frag_offset(warp)) ^ (i << 5), q[4 * i], q[4 * i + 1], q[4 * i + 2], q[4 * i + 3]);
        keep(q);
        bar_sync(2 + wg, 256);
        wg_fence();
#pragma unroll
        for (int kk = 0; kk < 8; kk++) mma_ss<1>(o, (kk < 4 ? da0 : da1) + (kk & 3) * 2, (kk < 4 ? db0 : db1) + UNIT / 16 + (kk & 3) * 128, 1);
        wg_commit();
        mbar_wait(bfull, 0);
        wg_fence();
        const uint64_t dk = make_desc(base + unit_of(at, 0), 16, 1024);
#pragma unroll
        for (int kk = 0; kk < 8; kk++) mma_rs<0>(s, q[4 * kk], q[4 * kk + 1], q[4 * kk + 2], q[4 * kk + 3], dk + (kk >> 2) * 1024 + (kk & 3) * 2, kk != 0);
        wg_commit();
        bar_arrive(3 - wg, 256);
#pragma unroll
        for (int i = 4; i < 8; i++) stmatrix4((qw + unit_of(qt, 1) + frag_offset(warp)) ^ ((i & 3) << 5), q[4 * i], q[4 * i + 1], q[4 * i + 2], q[4 * i + 3]);
        wg_wait<1>();
        keep(o);
        mbar_arrive_cl(rempty, GE + 16);
        mbar_arrive_cl(rempty, GE + 24);
        store_chunk<0>(o, qw + unit_of(qt, 2) + frag_offset(warp));
        store_chunk<1>(o, qw + unit_of(qt, 3) + frag_offset(warp));
        wg_wait<0>();
        keep(s);
        mbar_arrive_cl(rempty, 0);
      }
      PROF(4, tid == 0 && ps == 1, 61);
      float l0 = 0.f, l1 = 0.f, f0 = 0.f, f1 = 0.f;
      auto step = [&](auto odd_c, const int j, uint32_t (&pw)[32], uint32_t (&pr)[32]) {
        constexpr bool ODD = decltype(odd_c)::value;
        const bool first = !ODD && (j & 2) == 0, last = ODD && j == 7;
        const uint32_t ph = (j >> 1) & 1;
        float i0, i1, a0, a1;
        const bool so = !ODD && j == 4;
        if (so) { i0 = inv_quad_sum(l0); i1 = inv_quad_sum(l1); l0 = 0.f; l1 = 0.f; }
        if (first) {
          int m0 = max(__float_as_int(s[0]), __float_as_int(s[1])), m1 = max(__float_as_int(s[2]), __float_as_int(s[3]));
#pragma unroll
          for (int i = 1; i < 16; i++) {
            m0 = __vimax3_s32(m0, __float_as_int(s[4 * i]), __float_as_int(s[4 * i + 1]));
            m1 = __vimax3_s32(m1, __float_as_int(s[4 * i + 2]), __float_as_int(s[4 * i + 3]));
          }
          m0 = max(m0, __shfl_xor_sync(0xffffffffu, m0, 1)); m1 = max(m1, __shfl_xor_sync(0xffffffffu, m1, 1));
          m0 = max(m0, __shfl_xor_sync(0xffffffffu, m0, 2)); m1 = max(m1, __shfl_xor_sync(0xffffffffu, m1, 2));
          f0 = fmaf(__int_as_float(m0), SCL2, BIAS); f1 = fmaf(__int_as_float(m1), SCL2, BIAS);
        }
        bool redo = false;
        while (true) {
          if (redo) {
            float m0 = fmaxf(s[0], s[1]), m1 = fmaxf(s[2], s[3]);
#pragma unroll
            for (int i = 1; i < 16; i++) { m0 = fmaxf(m0, fmaxf(s[4 * i], s[4 * i + 1])); m1 = fmaxf(m1, fmaxf(s[4 * i + 2], s[4 * i + 3])); }
            m0 = fmaxf(m0, __shfl_xor_sync(0xffffffffu, m0, 1)); m1 = fmaxf(m1, __shfl_xor_sync(0xffffffffu, m1, 1));
            m0 = fmaxf(m0, __shfl_xor_sync(0xffffffffu, m0, 2)); m1 = fmaxf(m1, __shfl_xor_sync(0xffffffffu, m1, 2));
            m0 = fmaf(m0, SCL2, BIAS); m1 = fmaf(m1, SCL2, BIAS);
            if (!first) {
              m0 = fmaxf(m0, f0); m1 = fmaxf(m1, f1);
              const float c0 = ex2(f0 - m0), c1 = ex2(f1 - m1);
              l0 *= c0; l1 *= c1;
              wg_wait<0>();
              keep(o);
#pragma unroll
              for (int i = 0; i < 16; i++) { o[4 * i] *= c0; o[4 * i + 1] *= c0; o[4 * i + 2] *= c1; o[4 * i + 3] *= c1; }
            }
            f0 = m0; f1 = m1;
          }
          float b0 = 0.f, b1 = 0.f;
          a0 = 0.f; a1 = 0.f;
#pragma unroll
          for (int i = 0; i < 16; i++) {
            const float e0 = ex2(fmaf(s[4 * i], SCL2, -f0)), e1 = ex2(fmaf(s[4 * i + 1], SCL2, -f0));
            const float e2 = ex2(fmaf(s[4 * i + 2], SCL2, -f1)), e3 = ex2(fmaf(s[4 * i + 3], SCL2, -f1));
            a0 += e0; b0 += e1; a1 += e2; b1 += e3;
            pw[2 * i] = pack_bf(e0, e1); pw[2 * i + 1] = pack_bf(e2, e3);
            if (i == VREL) {
#pragma unroll
              for (int k = 0; k < 2 * VREL + 2; k++) asm volatile("" : "+r"(pw[k])::"memory");
              mbar_wait(bar_mod, 0);
              wg_wait<0>();
              mbar_arrive_cl(rempty, ODD ? 16 : 0, !redo && (ODD || j));
#pragma unroll
              for (int k = 4 * VREL + 4; k < 64; k++) asm volatile("" : "+f"(s[k])::"memory");
            }
          }
          a0 += b0; a1 += b1;
          if (redo) break;
          redo = __any_sync(0xffffffffu, !(a0 + a1 < 1.f));
          if (!redo) break;
        }
        l0 += a0; l1 += a1;
        keep(pw);
        keep(o);
        if (so) store_chunk<0>(o, i0, i1, qw + unit_of(qt, 0) + frag_offset(warp));
        keep(o);
        if (j == (ODD ? 5 : 0)) { fence_async_smem(); if (ODD) mbar_arrive(bar_ofull + wg * 8); }
        mbar_wait(bfull + (ODD ? 24 : 8), ph);
        bar_sync(2 + wg, 256);
        if (!last) {
          const uint32_t qn = qt >> (j >= 3 ? 8 : 0);
          wg_fence();
          issue_qk(s, qw + unit_of(qn, 0), qw + unit_of(qn, 1), base + unit_of(at, ODD ? 3 : 1));
          wg_commit();
          mbar_wait(bfull + (ODD ? 0 : 16), ODD ? ph ^ 1 : ph);
        }
        if (so) { store_chunk<1>(o, i0, i1, qw + unit_of(qt, 1) + frag_offset(warp)); keep(o); }
        wg_fence();
        issue_pv(o, pw, base + unit_of(at, ODD ? (last ? 3 : 0) : 2), !first);
        wg_commit();
        bar_arrive(3 - wg, 256);
        wg_wait<1>();
        keep(s);
        mbar_arrive_cl(rempty, ODD ? 24 : 8, !last);
        PROF(4, tid == 0 && ps == 1, 51 + j);
      };
      uint32_t pa[32], pb[32];
#pragma unroll 1
      for (int j = 0; j < 8; j += 2) {
        step(std::false_type{}, j, pa, pb);
        step(std::true_type{}, j + 1, pb, pa);
      }
      {
        const float i0 = inv_quad_sum(l0), i1 = inv_quad_sum(l1);
        wg_wait<0>();
        keep(o);
        mbar_arrive_cl(rempty, 24);
        store_chunk<0>(o, i0, i1, qw + unit_of(qt, 2) + frag_offset(warp));
        store_chunk<1>(o, i0, i1, qw + unit_of(qt, 3) + frag_offset(warp));
        fence_async_smem();
        mbar_arrive(bar_ofull + 16 + wg * 8);
      }
      PROF(2, tid == 0, 10 + ps * 8);
    }

    const int ln = fresh_lane(), g = ln >> 2, tq = ln & 3, ct = warp * 32 + ln;
    const bool lane0 = ln == 0;
    const int lrow0 = warp * 16 + g;
    const uint32_t res = base + OFF_RES, trow = res + wg * 8192 + frag_offset(warp);
    uint32_t xr[32];
    uint4 sv[4], own;
    uint32_t* const sg = g_stats + (rb * 8 + warp) * 512 + g * 4;
    uint32_t* sp[4];
#pragma unroll
    for (int k = 0; k < 4; k++) sp[k] = sg + (tq & 1) * 32 + (((tq >> 1) ^ (cj >> 2)) * 4 + (k ^ (cj & 3))) * 64;
    {
      const uint64_t da = make_desc(base + wg * 8192, 16, 1024), db = make_desc(base, 8192, 1024);
      constexpr int U = UNIT / 16;
#define HALF_STAGE(acc, xu, wu) _Pragma("unroll") for (int kk = 0; kk < 4; kk++) mma_ss<1>(acc, da + (xu) * U + kk * 2, db + (wu) * U + kk * 128, 1)
      PROF(10, ct == PT, 19); STAMP(0);
      cluster_arrive();
      mbar_wait(gfull, 1);
      mbar_wait(gfull + 8, 1);
      bar_sync(2 + wg, 256);
      wg_fence();
      HALF_STAGE(o, 7, 1);
      HALF_STAGE(o, 8, 3);
      wg_commit();
      STAMP(16);
      mbar_wait(gfull + 16, 1);
      STAMP(17);
      wg_fence();
      HALF_STAGE(o, 6, 11);
      wg_commit();
      bar_arrive(3 - wg, 256);
      mbar_wait(bar_par, 0);
      uint32_t* xo = g_xch + ((size_t)b * 8 * 256 + ct) * 4;
      const uint32_t* xi = g_xch + ((size_t)(b ^ 2) * 8 * 256 + ct) * 4;
      const uint32_t par1 = (~lds1(par + PAR_CONST + 4) & 1) << 16;
      wg_wait<1>();
      mbar_arrive_pred(bar_rel, lane0);
      wg_wait<0>();
      keep(o);
      mbar_arrive_pred(bar_ring, lane0);
      PROF(8, ct == PT, 20); STAMP(1);
#define SEND(i) st_b128(xo + (i) * 1024, (pack_bf(o[8 * (i)], o[8 * (i) + 1]) & ~0x10000u) | par1, pack_bf(o[8 * (i) + 2], o[8 * (i) + 3]), \
                        pack_bf(o[8 * (i) + 4], o[8 * (i) + 5]), pack_bf(o[8 * (i) + 6], o[8 * (i) + 7]))
#pragma unroll
      for (int i = 0; i < NS1; i++) SEND(i);
      PROF(8, ct == PT, 21); STAMP(2);
      bar_sync(2 + wg, 256);
      wg_fence();
      HALF_STAGE(s, 7, 0);
      HALF_STAGE(s, 8, 2);
      HALF_STAGE(s, 6, 10);
      wg_commit();
      bar_arrive(3 - wg, 256);
      STAMP(18);
      mbar_wait(gfull + 24, 1);
#pragma unroll
      for (int i = NS1; i < 8; i++) SEND(i);
      uint4 v[8];
      STAMP(19);
      mbar_wait(bar_xres, 0);
      wg_wait<0>();
      mbar_arrive_pred(bar_ring + 8, lane0);
      bar_sync(2 + wg, 256);
      STAMP(20);
#pragma unroll
      for (int i = 0; i < LD2; i++) v[i] = ld_b128(xi + i * 1024);
      mbar_wait(bar_xres, 0);
      wg_fence();
      HALF_STAGE(s, 9, 4);
      wg_commit();
      mbar_wait(bar_rx, 0);
      wg_fence();
      HALF_STAGE(s, 1, 5);
      wg_commit();
      bar_arrive(3 - wg, 256);
      STAMP(21);
#pragma unroll
      for (int i = LD2; i < 8; i++) v[i] = ld_b128(xi + i * 1024);
      mbar_wait(bar_xres, 0);
      wg_wait<0>();
      keep(s);
      mbar_arrive_pred(bar_ring + 16, lane0);
      PROF(10, ct == PT, 23); STAMP(4);
#pragma unroll
      for (int i = 0; i < 16; i += 2) ldmatrix4((trow ^ ((i & 7) << 4)) + (i >> 3) * 16384, xr[2 * i], xr[2 * i + 1], xr[2 * i + 2], xr[2 * i + 3]);
      uint32_t ga[16];
      uint4 bw[8];
#pragma unroll
      for (int i = 0; i < 8; i++) {
        if (!(i & 1)) {
          const uint4 t = lds4(par + PAR_SINK + i * 32 + tq * 16);
          ga[2 * i] = t.x; ga[2 * i + 1] = t.y; ga[2 * i + 2] = t.z; ga[2 * i + 3] = t.w;
        }
        bw[i] = lds4(par + PAR_T1 + i * 64 + tq * 16);
        if (!(g & 1)) { bw[i].x = 0x3f803f80u; bw[i].y = 0x3f803f80u; }
      }
      uint32_t pk[32];
      pack_p(s, pk);
      const uint32_t par2 = (~lds1(par + PAR_CONST + 12) & 1) << 16;
      {
        uint32_t n = 0, miss;
        do {
          miss = 0;
#pragma unroll
          for (int i = 0; i < 8; i++) miss |= v[i].x ^ par2;
          miss = __any_sync(0xffffffffu, miss & 0x10000u);
          if (miss) {
#pragma unroll
            for (int i = 0; i < 8; i++)
              asm volatile("{ .reg .pred p; .reg .b32 t; xor.b32 t, %0, %5; and.b32 t, t, 0x10000; setp.ne.u32 p, t, 0;\n"
                           "@p ld.relaxed.gpu.global.v4.u32 {%0, %1, %2, %3}, [%4]; }"
                           : "+r"(v[i].x), "+r"(v[i].y), "+r"(v[i].z), "+r"(v[i].w) : "l"(xi + i * 1024), "r"(par1) : "memory");
          }
          watchdog(n);
        } while (miss);
      }
      PROF(8, ct == PT, 22); STAMP(3);
      float ds[4] = {0.f, 0.f, 0.f, 0.f}, dl[4] = {0.f, 0.f, 0.f, 0.f}, q0[4] = {0.f, 0.f, 0.f, 0.f}, q1[4] = {0.f, 0.f, 0.f, 0.f};
#pragma unroll
      for (int i = 0; i < 8; i++) {
        const uint32_t u0 = hfma2(ga[2 * i], hadd2(pk[4 * i], v[i].x & ~0x10000u), xr[4 * i]);
        const uint32_t u1 = hfma2(ga[2 * i], hadd2(pk[4 * i + 1], v[i].y), xr[4 * i + 1]);
        const uint32_t u2 = hfma2(ga[2 * i + 1], hadd2(pk[4 * i + 2], v[i].z), xr[4 * i + 2]);
        const uint32_t u3 = hfma2(ga[2 * i + 1], hadd2(pk[4 * i + 3], v[i].w), xr[4 * i + 3]);
        xr[4 * i] = u0; xr[4 * i + 1] = u1; xr[4 * i + 2] = u2; xr[4 * i + 3] = u3;
        mma16816(ds, u0, u1, u2, u3, bw[i].x, bw[i].y);
        mma16816(dl, u0, u1, u2, u3, bw[i].z, bw[i].w);
        mma16816(q0, u0, u1, u2, u3, u0, u2);
        mma16816(q1, u0, u1, u2, u3, u1, u3);
      }
      const float sqa = (g & 1) ? q0[1] : q0[0], sqb = (g & 1) ? q1[3] : q1[2], dta = ds[1] + dl[1], dtb = ds[3] + dl[3];
      if (tq == (g >> 1)) {
        st_b128(sg + cj * 64, __float_as_uint(ds[0]), __float_as_uint(sqa), __float_as_uint(dta), tag);
        st_b128(sg + cj * 64 + 32, __float_as_uint(ds[2]), __float_as_uint(sqb), __float_as_uint(dtb), tag);
      }
#pragma unroll
      for (int k = 0; k < 4; k++) sv[k] = ld_b128(sp[k]);
      mbar_wait(bar_xres, 0);
      const float sqc = __shfl_sync(0xffffffffu, sqa, g * 4 + (g >> 1)), sqd = __shfl_sync(0xffffffffu, sqb, g * 4 + (g >> 1));
      own = (tq & 1) ? make_uint4(__float_as_uint(ds[2]), __float_as_uint(sqd), __float_as_uint(dtb), tag)
                     : make_uint4(__float_as_uint(ds[0]), __float_as_uint(sqc), __float_as_uint(dta), tag);
    }
    PROF(8, ct == PT, 29); STAMP(5);
    uint32_t mm, ih, il;
    float rbest;
    uint32_t wf[128];
    const uint32_t frow = (ln & 7) + (ln >> 4) * 8;
    const uint32_t wfo = base + (warp & 1) * 8192 + frow * 64 + ((((ln >> 3) & 1) ^ ((frow >> 1) & 3)) << 4);
#define LOAD_WF(m) _Pragma("unroll") for (int f = 0; f < 16; f++) {                                                   \
      const int r = ((f >> 1) * 4 + (m) * 2 + (f & 1)) * 4;                                                           \
      ldmatrix4t(((wfo + unit_of((m) ? FT_U : FT_G, warp >> 1)) ^ ((f & 1) * 32)) + (f >> 1) * 1024, wf[r], wf[r + 1], wf[r + 2], wf[r + 3]); \
    }
    bool early;
    {
#pragma unroll
      for (int i = 0; i < 16; i += 2) stmatrix4((trow ^ ((i & 7) << 4)) + (i >> 3) * 16384, xr[2 * i], xr[2 * i + 1], xr[2 * i + 2], xr[2 * i + 3]);
      const uint4 cst = lds4(par + PAR_CONST);
      const float A1 = __uint_as_float(cst.x), A2 = __uint_as_float(cst.z);
      uint32_t n = 0;
      early = false;
#pragma unroll 1
      while (true) {
        if (!early && (b >= NFFN || __all_sync(0xffffffffu, mbar_test(bar_box + (warp >> 1) * 8, 0)))) {
          early = true;
          LOAD_WF(0);
          __syncwarp();
          mbar_arrive_pred(bar_gate, lane0);
        }
        uint32_t miss;
        asm volatile("{ .reg .pred p0, p1, p2, p3; .reg .b64 u, v; .reg .b128 w;\n"
                     "setp.ge.u32 p0, %22, 2; setp.ne.and.u32 p0, %4, %21, p0; setp.ne.u32 p1, %8, %21; setp.ne.u32 p2, %12, %21; setp.ne.u32 p3, %16, %21;\n"
                     "@p0 ld.relaxed.gpu.global.v4.u32 {%1, %2, %3, %4}, [%17];\n"
                     "@p1 ld.relaxed.gpu.global.v4.u32 {%5, %6, %7, %8}, [%18];\n"
                     "@p2 ld.relaxed.gpu.global.v4.u32 {%9, %10, %11, %12}, [%19];\n"
                     "@p3 ld.relaxed.gpu.global.v4.u32 {%13, %14, %15, %16}, [%20];\n"
                     "or.pred p0, p0, p1; or.pred p2, p2, p3; or.pred p0, p0, p2; vote.sync.any.pred p0, p0, 0xffffffff; selp.u32 %0, 1, 0, p0; }"
                     : "=r"(miss), "+r"(sv[0].x), "+r"(sv[0].y), "+r"(sv[0].z), "+r"(sv[0].w), "+r"(sv[1].x), "+r"(sv[1].y), "+r"(sv[1].z), "+r"(sv[1].w),
                       "+r"(sv[2].x), "+r"(sv[2].y), "+r"(sv[2].z), "+r"(sv[2].w), "+r"(sv[3].x), "+r"(sv[3].y), "+r"(sv[3].z), "+r"(sv[3].w)
                     : "l"(sp[0]), "l"(sp[1]), "l"(sp[2]), "l"(sp[3]), "r"(tag), "r"(tq) : "memory");
        if (!miss) break;
        watchdog(n);
      }
      const uint4 v0 = tq < 2 ? own : sv[0], v1 = sv[1], v2 = sv[2], v3 = sv[3];
      PROF(8, ct == PT, 30); STAMP(6);
      float su = (__uint_as_float(v0.x) + __uint_as_float(v1.x)) + (__uint_as_float(v2.x) + __uint_as_float(v3.x));
      float sq = (__uint_as_float(v0.y) + __uint_as_float(v1.y)) + (__uint_as_float(v2.y) + __uint_as_float(v3.y));
      float dt = (__uint_as_float(v0.z) + __uint_as_float(v1.z)) + (__uint_as_float(v2.z) + __uint_as_float(v3.z));
      su += __shfl_xor_sync(0xffffffffu, su, 2); sq += __shfl_xor_sync(0xffffffffu, sq, 2); dt += __shfl_xor_sync(0xffffffffu, dt, 2);
      const float m = su * (1.f / DM);
      float mb, sd;
      ln_scalars(m, fmaxf(sq * (1.f / DM) - m * m, 0.f), mb, sd);
      const float inv = rcp(sd);
      rbest = (dt - mb * A1) * inv + A2;
      mm = pack_bf(mb, mb);
      ih = pack_bf(inv, inv);
      const float lo = inv - bf_lo(ih);
      il = pack_bf(lo, lo);
    }
    int ibest;
    {
      const uint32_t bits = __float_as_uint(rbest);
      const uint32_t key = (((int)bits < 0 ? ~bits : bits | 0x80000000u) & ~0x1ffu) | ((127 - lrow0 - (tq & 1) * 8) << 2) | tag;
      sts1(par + PAR_RED + warp * 4, __reduce_max_sync(0xffffffffu, key));
      PROF(8, ct == PT, 38); STAMP(7);
      bar_sync(1, 256);
      const uint4 ka = lds4(par + PAR_RED), kb = lds4(par + PAR_RED + 16);
      const uint32_t k2 = max(max(max(ka.x, ka.y), max(ka.z, ka.w)), max(max(kb.x, kb.y), max(kb.z, kb.w)));
      if (ct < CR && cj == 0) st_relaxed(g_cand + ct * 512 + rb * CS, k2);
      ibest = 127 - ((k2 >> 2) & 127);
    }
    PROF(8, ct == PT, 39); STAMP(8);
    if ((ibest >> 4) == warp) {
      const int src = (ibest & 7) * 4 + ((ibest >> 3) & 1), ch = g * 2;
      const uint32_t cm = __shfl_sync(0xffffffffu, mm, src), ch_ = __shfl_sync(0xffffffffu, ih, src), cl = __shfl_sync(0xffffffffu, il, src);
      const uint32_t xa = res + (ch >> 3) * 16384 + ibest * 128 + (((ch & 7) ^ (ibest & 7)) << 4) + tq * 4;
      const uint32_t x0 = lds1(xa), x1 = lds1(xa ^ 16);
      const uint2 p0 = lds2(par + PAR_T2 + ch * 64 + tq * 16), p1 = lds2(par + PAR_T2 + ch * 64 + 64 + tq * 16);
      uint32_t* dst = g_row + rb * 2 * DM + cj * 128 + ln * 4;
      st_pairs(dst, ln_mod(x0, cm, ch_, cl, p0.x, p0.y), ln_mod(x1, cm, ch_, cl, p1.x, p1.y), tag);
      st_pairs(dst + DM, x0, x1, tag);
      __syncwarp();
    }
    PROF(8, ct == PT, 37); STAMP(9);
    uint32_t wd[64];
    const uint32_t wda = base + unit_of(FT_D, warp >> 1) + (warp & 1) * 8192 + frow * 128 + ((((ln >> 3) & 1) ^ (ln & 7)) << 4);
#define LOAD_WD(f) ldmatrix4t((wda ^ ((((f) >> 1) & 3) * 32)) + ((f) >> 3) * 4096 + ((f) & 1) * 2048, wd[4 * (f)], wd[4 * (f) + 1], wd[4 * (f) + 2], wd[4 * (f) + 3])
    if (!early) {
      if (b < NFFN) mbar_wait(bar_box + (warp >> 1) * 8, 0);
      LOAD_WF(0);
      __syncwarp();
      mbar_arrive_pred(bar_gate, lane0);
    }
    if (b < NFFN) {
      const uint32_t own = base + unit_of(FT_G, warp >> 1) + (warp & 1) * 8192;
      mbar_wait(bar_box + (4 + (warp >> 1)) * 8, 0);
      LOAD_WF(1);
      uint32_t* const ydst = ypart_slot(b, warp * 16 + (tq & 1) * 8 + g);
      PROF(8, ct == PT, 31); STAMP(10);
      bool wdok;
      {
        uint32_t n = 0;
        while (!(wdok = __all_sync(0xffffffffu, mbar_test(bar_box + (8 + (warp >> 1)) * 8, 0))) && !__all_sync(0xffffffffu, mbar_test(bar_sel, 0))) watchdog(n);
      }
      if (wdok) {
#pragma unroll
        for (int f = 0; f < 16; f++) LOAD_WD(f);
      }
      STAMP(11);
      mbar_wait(bar_sel, 0);
      PROF(8, ct == PT, 33); STAMP(12);
      float d[8][4];
#pragma unroll
      for (int i = 0; i < 4; i++) { d[i][0] = 0.f; d[i][1] = 0.f; d[i][2] = 0.f; d[i][3] = 0.f; }
#pragma unroll
      for (int ks = 0; ks < 8; ks++) {
        const uint2 hb = lds2(own + 256 + ks * 32 + tq * 8);
#pragma unroll
        for (int mt = 0; mt < 4; mt++) {
          const int r = ks * 16 + mt * 4;
          mma16816(d[mt], wf[r], wf[r + 1], wf[r + 2], wf[r + 3], hb.x, hb.y);
        }
      }
      sts2(own + (tq * 8 + g) * 8, __float_as_uint((tq & 2) ? ((tq & 1) ? d[1][2] : d[1][0]) : ((tq & 1) ? d[0][2] : d[0][0])),
           __float_as_uint((tq & 2) ? ((tq & 1) ? d[3][2] : d[3][0]) : ((tq & 1) ? d[2][2] : d[2][0])));
      bar_sync(1, 256);
      uint32_t ab[4];
      {
        float G = 0.f, U = 0.f;
        uint2 pv[8];
#pragma unroll
        for (int w8 = 0; w8 < 8; w8++) pv[w8] = lds2(base + ln * 8 + ((FT_G >> (w8 >> 1) * 4) & 15) * UNIT + (w8 & 1) * 8192);
#pragma unroll
        for (int w8 = 0; w8 < 8; w8 += 2) {
          G += __uint_as_float(pv[w8].x) + __uint_as_float(pv[w8 + 1].x);
          U += __uint_as_float(pv[w8].y) + __uint_as_float(pv[w8 + 1].y);
        }
        const float act = rbf(silu_f(rbf(G))) * rbf(U);
        const uint32_t pk = pack_bf(act, __shfl_down_sync(0xffffffffu, act, 1));
#pragma unroll
        for (int i = 0; i < 4; i++) ab[i] = __shfl_sync(0xffffffffu, pk, i * 8 + tq * 2);
      }
      if (!wdok) {
        mbar_wait(bar_box + (8 + (warp >> 1)) * 8, 0);
#pragma unroll
        for (int f = 0; f < 16; f++) LOAD_WD(f);
      }
      PROF(8, ct == PT, 34); STAMP(13);
#pragma unroll
      for (int mt = 0; mt < 8; mt++) {
        d[mt][0] = 0.f; d[mt][1] = 0.f; d[mt][2] = 0.f; d[mt][3] = 0.f;
        mma16816(d[mt], wd[mt * 8], wd[mt * 8 + 1], wd[mt * 8 + 2], wd[mt * 8 + 3], ab[0], ab[1]);
        mma16816(d[mt], wd[mt * 8 + 4], wd[mt * 8 + 5], wd[mt * 8 + 6], wd[mt * 8 + 7], ab[2], ab[3]);
      }
      uint32_t yw[4];
#pragma unroll
      for (int i = 0; i < 4; i++) yw[i] = (tq & 1) ? pack_bf(d[2 * i][2], d[2 * i + 1][2]) : pack_bf(d[2 * i][0], d[2 * i + 1][0]);
      if (tq < 2) st_b128(ydst, (yw[0] & ~1u) | (tag & 1), (yw[1] & ~1u) | (tag >> 1), yw[2], yw[3]);
      PROF(8, ct == PT, 35); STAMP(14);
    }
    mbar_wait(bar_sel, 0);
    mbar_arrive_pred(bar_win, ct == 0);
    const int iwin = lds1(par + PAR_CONST + 60) & 0x7ff;
    const bool cand = (iwin >> 4) == rb * 8 + warp;
    {
      const uint32_t mm0 = __shfl_sync(0xffffffffu, mm, ln & ~1), mm1 = __shfl_sync(0xffffffffu, mm, ln | 1);
      const uint32_t ih0 = __shfl_sync(0xffffffffu, ih, ln & ~1), ih1 = __shfl_sync(0xffffffffu, ih, ln | 1);
      const uint32_t il0 = __shfl_sync(0xffffffffu, il, ln & ~1), il1 = __shfl_sync(0xffffffffu, il, ln | 1);
#pragma unroll 1
      for (int hf = 0; hf < 2; hf++) {
        uint32_t x[16];
#pragma unroll
        for (int i = 0; i < 8; i += 2) ldmatrix4((trow ^ (i << 4)) + hf * 16384, x[2 * i], x[2 * i + 1], x[2 * i + 2], x[2 * i + 3]);
#pragma unroll
        for (int i = 0; i < 8; i++) {
          const uint4 pv = lds4(par + PAR_T2 + (hf * 8 + i) * 64 + tq * 16);
          x[2 * i] = hfma2(hfma2(ln_norm(x[2 * i], mm0, ih0, il0), pv.x, pv.y), pv.z, x[2 * i]);
          x[2 * i + 1] = hfma2(hfma2(ln_norm(x[2 * i + 1], mm1, ih1, il1), pv.x, pv.y), pv.z, x[2 * i + 1]);
        }
#pragma unroll
        for (int i = 0; i < 8; i += 2) stmatrix4((trow ^ (i << 4)) + hf * 16384, x[2 * i], x[2 * i + 1], x[2 * i + 2], x[2 * i + 3]);
        if (!cand) fence_async_smem();
        __syncwarp();
        if (!cand && elect_one()) {
          tma2d_store(&maps.out, res + hf * 16384 + warp * 2048, cj * 128 + hf * 64, rb * 128 + warp * 16);
          asm volatile("cp.async.bulk.commit_group;" ::: "memory");
        }
      }
    }
    if (cand) {
      const int wrow0 = warp * 16;
#pragma unroll 2
      for (int p = 0; p < 8; p++) {
        const int row = 2 * p + (ln >> 4), ch = ln & 15;
        const uint4 v = lds4(res + (ch >> 3) * 16384 + (wrow0 + row) * 128 + (((ch & 7) ^ (row & 7)) << 4));
        if (rb * 128 + wrow0 + row != iwin) *reinterpret_cast<uint4*>(P.out + (size_t)(rb * 128 + wrow0 + row) * DM + cj * 128 + ch * 8) = v;
      }
    }
    asm volatile("cp.async.bulk.wait_group.read 0;" ::: "memory");
    PROF(8, ct == PT, 11); STAMP(15);
    cluster_wait();
  }
}

typedef CUresult (*EncodeFn)(CUtensorMap*, CUtensorMapDataType, cuuint32_t, void*, const cuuint64_t*, const cuuint64_t*,
                             const cuuint32_t*, const cuuint32_t*, CUtensorMapInterleave, CUtensorMapSwizzle,
                             CUtensorMapL2promotion, CUtensorMapFloatOOBfill);

void map2d(EncodeFn enc, CUtensorMap* m, const void* p, uint64_t rows, uint64_t cols, uint32_t brows) {
  cuuint64_t dims[2] = {cols, rows}, strides[1] = {cols * 2};
  cuuint32_t box[2] = {64, brows}, es[2] = {1, 1};
  enc(m, CU_TENSOR_MAP_DATA_TYPE_BFLOAT16, 2, const_cast<void*>(p), dims, strides, box, es, CU_TENSOR_MAP_INTERLEAVE_NONE,
      CU_TENSOR_MAP_SWIZZLE_128B, CU_TENSOR_MAP_L2_PROMOTION_L2_256B, CU_TENSOR_MAP_FLOAT_OOB_FILL_NONE);
}
void map2d_narrow(EncodeFn enc, CUtensorMap* m, const void* p, uint64_t rows, uint64_t cols, uint32_t brows) {
  cuuint64_t dims[2] = {cols, rows}, strides[1] = {cols * 2};
  cuuint32_t box[2] = {32, brows}, es[2] = {1, 1};
  enc(m, CU_TENSOR_MAP_DATA_TYPE_BFLOAT16, 2, const_cast<void*>(p), dims, strides, box, es, CU_TENSOR_MAP_INTERLEAVE_NONE,
      CU_TENSOR_MAP_SWIZZLE_64B, CU_TENSOR_MAP_L2_PROMOTION_L2_64B, CU_TENSOR_MAP_FLOAT_OOB_FILL_NONE);
}
void map3d(EncodeFn enc, CUtensorMap* m, const void* p, uint64_t rows, uint64_t cols, uint32_t brows, uint32_t nch) {
  cuuint64_t dims[3] = {64, rows, cols / 64}, strides[2] = {cols * 2, 128};
  cuuint32_t box[3] = {64, brows, nch}, es[3] = {1, 1, 1};
  enc(m, CU_TENSOR_MAP_DATA_TYPE_BFLOAT16, 3, const_cast<void*>(p), dims, strides, box, es, CU_TENSOR_MAP_INTERLEAVE_NONE,
      CU_TENSOR_MAP_SWIZZLE_128B, CU_TENSOR_MAP_L2_PROMOTION_L2_256B, CU_TENSOR_MAP_FLOAT_OOB_FILL_NONE);
}

}

extern "C" void kernel_launch(void* const* d_in, const int* in_sizes, int n_in, void* d_out, int out_size) {
  (void)in_sizes; (void)n_in; (void)out_size;
  static EncodeFn enc = nullptr;
  if (!enc) {
    void* fn = nullptr;
    cudaDriverEntryPointQueryResult st;
    cudaGetDriverEntryPoint("cuTensorMapEncodeTiled", &fn, cudaEnableDefault, &st);
    enc = (EncodeFn)fn;
    cudaFuncSetAttribute(fused_kernel, cudaFuncAttributeMaxDynamicSharedMemorySize, SMEM_BYTES);
  }
  Maps maps;
  map2d(enc, &maps.x, d_in[0], SEQ, DM, 128);
  map2d(enc, &maps.out, d_out, SEQ, DM, 16);
  map3d(enc, &maps.wq, d_in[3], DM, NQ, 64, 2);
  map3d(enc, &maps.k, d_in[1], 4 * SK, 128, 128, 1);
  map3d(enc, &maps.v, d_in[2], 4 * SK, 128, 128, 1);
  map3d(enc, &maps.wo, d_in[4], NQ, DM, 64, 2);
  map2d_narrow(enc, &maps.wg, d_in[7], DM, FF, 256);
  map2d_narrow(enc, &maps.wu, d_in[8], DM, FF, 256);
  map3d(enc, &maps.wd, d_in[9], FF, DM, 32, 4);
  map2d_narrow(enc, &maps.wm, d_in[11], DM, NMOD, 256);
  Ptrs p;
  p.x = (const __nv_bfloat16*)d_in[0];
  p.w_r = (const __nv_bfloat16*)d_in[6];
  p.w_gate = (const __nv_bfloat16*)d_in[7];
  p.w_up = (const __nv_bfloat16*)d_in[8];
  p.w_down = (const __nv_bfloat16*)d_in[9];
  p.c = (const __nv_bfloat16*)d_in[10];
  p.w_mod = (const __nv_bfloat16*)d_in[11];
  p.out = (__nv_bfloat16*)d_out;
  fused_kernel<<<NMAIN + NHELP, 384, SMEM_BYTES>>>(maps, p);
}
```

```cpp
#include <cuda_runtime.h>
#include <cuda_bf16.h>
#include <cuda.h>
#include <stdint.h>
#include <type_traits>

#define HD 2
#define HDX 2
#define NRS 8
#define OSL 900
#define OSL2 400
#define RSL 40
#define BIAS 96.f
#define GL 1
#define OST 3
#define HWB 0
#define VREL 5
#define OPS 8192
#define ODS1 5
#define ODS 7
#define PG0 15
#define WB 2
#define WN 20
#define HU 32
#define RES0 17
#define RES1 20
#define GOST 20
#define NS1 5
#define LD2 4
#define FPACE0 2
#define FPACE 3
#define CR 8
#define CS 8

namespace {

constexpr int SEQ = 2048, DM = 1024, NQ = 4096, SK = 2048, WIN = 512, FF = 3584, NMOD = 6144;
constexpr int NMAIN = 128, NHELP = 4, NFFN = 112;
constexpr int NSLOT = 4, SLOT_BYTES = 32768, UNIT = 16384, GST_BYTES = 3 * UNIT;
constexpr uint32_t XT1 = 0xDCBA, XT2 = 0x9687;
constexpr uint32_t WT0 = 0xA741, WT1 = 0x7420, WT2 = 0x4A20;
constexpr uint32_t AT0 = WT1, AT1 = WT2;
constexpr uint32_t QT = 0xDC9696DC;
constexpr int OFF_STAGE = 12 * UNIT;
constexpr uint32_t FT_G = 0x07B3, FT_U = 0xA628, FT_D = 0x5149;
constexpr int OFF_RES = 12 * UNIT;
constexpr int OFF_PAR = 14 * UNIT;
constexpr int OFF_BAR = OFF_PAR + 2528;
constexpr int SMEM_BYTES = OFF_BAR + 544;
static_assert(SMEM_BYTES <= 232448, "smem");

constexpr int PAR_T1 = 0;
constexpr int PAR_T2 = 512;
constexpr int PAR_CONST = 1536;
constexpr int PAR_RED = 1600;
constexpr int PAR_SINK = 2176;

struct Maps {
  CUtensorMap x, wq, k, v, wo, wg, wu, wd, wm, out;
};
struct Ptrs {
  const __nv_bfloat16 *x, *w_r, *c, *w_mod, *w_gate, *w_up, *w_down;
  __nv_bfloat16* out;
};

__device__ __align__(1024) uint8_t g_act[16 * 80 * UNIT];
__device__ __align__(128) uint32_t g_mod[NMOD];
__device__ __align__(128) uint32_t g_modp[2 * 2 * DM];
__device__ __align__(128) uint32_t g_ln1[SEQ * 4];
__device__ __align__(128) uint32_t g_cnt_h[16 * 32];
__device__ __align__(128) uint32_t g_cnt_o[128 * 32];
__device__ __align__(128) uint32_t g_xch[NMAIN * 8 * 256 * 4];
__device__ __align__(128) uint32_t g_stats[8 * SEQ * 4];
__device__ __align__(128) uint32_t g_cand[CR * 512];
__device__ __align__(128) uint32_t g_row[16 * 2 * DM];
__device__ __align__(128) uint32_t g_ypart[NMAIN * NFFN * 4];
__device__ __forceinline__ uint32_t* ypart_slot(int writer, int reader) { return g_ypart + (writer * NMAIN + reader) * 4; }
__device__ uint32_t g_epoch;

__device__ __forceinline__ uint32_t fresh_lane() { uint32_t l; asm volatile("mov.u32 %0, %%laneid;" : "=r"(l)); return l; }
__device__ __forceinline__ uint32_t frag_offset(int warp) {
  const uint32_t l = fresh_lane();
  return ((warp & 3) * 16 + (l & 15)) * 128 + (((l >> 4) ^ (l & 7)) << 4);
}
__device__ __forceinline__ bool elect_one() {
  uint32_t p;
  asm volatile("{ .reg .pred q; elect.sync _|q, 0xffffffff; selp.u32 %0, 1, 0, q; }" : "=r"(p));
  return p;
}
__device__ __forceinline__ uint32_t smem_u32(const void* p) { return (uint32_t)__cvta_generic_to_shared(p); }
__device__ __forceinline__ void mbar_init(uint32_t bar, uint32_t cnt) {
  asm volatile("mbarrier.init.shared::cta.b64 [%0], %1;" ::"r"(bar), "r"(cnt) : "memory");
}
__device__ __forceinline__ void mbar_expect_tx(uint32_t bar, uint32_t bytes) {
  asm volatile("mbarrier.arrive.expect_tx.shared::cta.b64 _, [%0], %1;" ::"r"(bar), "r"(bytes) : "memory");
}
__device__ __forceinline__ void mbar_arrive(uint32_t bar) {
  asm volatile("mbarrier.arrive.shared::cta.b64 _, [%0];" ::"r"(bar) : "memory");
}
__device__ __forceinline__ void mbar_arrive_pred(uint32_t bar, bool p) {
  asm volatile("{ .reg .pred p; setp.ne.b32 p, %1, 0; @p mbarrier.arrive.shared::cta.b64 _, [%0]; }" ::"r"(bar), "r"((int)p) : "memory");
}
__device__ __forceinline__ void mbar_arrive_cl(uint32_t bar, uint32_t off, bool p = true) {
  asm volatile("{ .reg .pred p, q; .reg .b32 a; setp.ne.b32 q, %2, 0; setp.ne.and.b32 p, %0, 0, q; add.u32 a, %0, %1; @p mbarrier.arrive.shared::cluster.b64 _, [a]; }"
               ::"r"(bar), "r"(off), "r"((int)p) : "memory");
}
__device__ __forceinline__ uint32_t mapa(uint32_t addr, uint32_t cta) {
  uint32_t r; asm("mapa.shared::cluster.u32 %0, %1, %2;" : "=r"(r) : "r"(addr), "r"(cta)); return r;
}
__device__ __forceinline__ void cluster_arrive() { asm volatile("barrier.cluster.arrive.relaxed.aligned;" ::: "memory"); }
__device__ __forceinline__ void cluster_wait() { asm volatile("barrier.cluster.wait.aligned;" ::: "memory"); }
__device__ __forceinline__ void watchdog(uint32_t& n) {
}
__device__ __forceinline__ void mbar_wait(uint32_t bar, uint32_t parity) {
  asm volatile("{\n.reg .pred p;\nWAIT_%=:\nmbarrier.try_wait.parity.shared::cta.b64 p, [%0], %1;\n@!p bra WAIT_%=;\n}" ::"r"(bar), "r"(parity) : "memory");
}
__device__ __forceinline__ bool mbar_test(uint32_t bar, uint32_t parity) {
  uint32_t ok;
  asm volatile("{\n.reg .pred p;\nmbarrier.test_wait.parity.shared::cta.b64 p, [%1], %2;\nselp.u32 %0, 1, 0, p;\n}" : "=r"(ok) : "r"(bar), "r"(parity) : "memory");
  return ok;
}
__device__ __forceinline__ uint64_t l2_stream() {
  uint64_t f; asm("createpolicy.fractional.L2::evict_first.b64 %0, 1.0;" : "=l"(f)); return f;
}
__device__ __forceinline__ uint64_t l2_normal() {
  uint64_t f; asm("createpolicy.fractional.L2::evict_normal.b64 %0, 1.0;" : "=l"(f)); return f;
}
__device__ __forceinline__ void tma2d(uint32_t dst, const CUtensorMap* m, int c0, int c1, uint32_t bar) {
  asm volatile("cp.async.bulk.tensor.2d.shared::cluster.global.mbarrier::complete_tx::bytes.L2::cache_hint [%0], [%1, {%3, %4}], [%2], %5;"
               ::"r"(dst), "l"(m), "r"(bar), "r"(c0), "r"(c1), "l"(l2_stream()) : "memory");
}
__device__ __forceinline__ void bulk_load(uint32_t dst, const void* src, uint32_t bytes, uint32_t bar) {
  asm volatile("cp.async.bulk.shared::cluster.global.mbarrier::complete_tx::bytes [%0], [%1], %2, [%3];" ::"r"(dst), "l"(src), "r"(bytes), "r"(bar) : "memory");
}
__device__ __forceinline__ void bulk_load_stream(uint32_t dst, const void* src, uint32_t bytes, uint32_t bar, uint64_t pol = l2_stream()) {
  asm volatile("cp.async.bulk.shared::cluster.global.mbarrier::complete_tx::bytes.L2::cache_hint [%0], [%1], %2, [%3], %4;"
               ::"r"(dst), "l"(src), "r"(bytes), "r"(bar), "l"(pol) : "memory");
}
__device__ __forceinline__ void tma2d_store(const CUtensorMap* m, uint32_t src, int c0, int c1) {
  asm volatile("cp.async.bulk.tensor.2d.global.shared::cta.bulk_group [%0, {%2, %3}], [%1];" ::"l"(m), "r"(src), "r"(c0), "r"(c1) : "memory");
}
__device__ __forceinline__ void bulk_store(void* dst, uint32_t src, uint32_t bytes) {
  asm volatile("cp.async.bulk.global.shared::cta.bulk_group [%0], [%1], %2;" ::"l"(dst), "r"(src), "r"(bytes) : "memory");
}
__device__ __forceinline__ int slice_of(int i) { return (i & 8) + (((OST == 2 ? 0x76543120u : OST == 3 ? 0x76531420u : 0x75316420u) >> (i & 7) * 4) & 7); }
__device__ __forceinline__ uint32_t unit_of(uint32_t table, uint32_t i) { return ((table >> (i * 4)) & 15) * UNIT; }
__device__ __forceinline__ void tma3d(uint32_t dst, const CUtensorMap* m, int c0, int c1, int c2, uint32_t bar) {
  asm volatile("cp.async.bulk.tensor.3d.shared::cluster.global.mbarrier::complete_tx::bytes.L2::cache_hint [%0], [%1, {%3, %4, %5}], [%2], %6;"
               ::"r"(dst), "l"(m), "r"(bar), "r"(c0), "r"(c1), "r"(c2), "l"(l2_stream()) : "memory");
}
template <bool STREAM>
__device__ __forceinline__ void tma3d_mc(uint32_t dst, const CUtensorMap* m, int c0, int c1, int c2, uint32_t bar) {
  if (STREAM)
    asm volatile("cp.async.bulk.tensor.3d.shared::cluster.global.mbarrier::complete_tx::bytes.multicast::cluster.L2::cache_hint [%0], [%1, {%3, %4, %5}], [%2], %6, %7;"
                 ::"r"(dst), "l"(m), "r"(bar), "r"(c0), "r"(c1), "r"(c2), "h"((uint16_t)3), "l"(l2_stream()) : "memory");
  else
    asm volatile("cp.async.bulk.tensor.3d.shared::cluster.global.mbarrier::complete_tx::bytes.multicast::cluster [%0], [%1, {%3, %4, %5}], [%2], %6;"
                 ::"r"(dst), "l"(m), "r"(bar), "r"(c0), "r"(c1), "r"(c2), "h"((uint16_t)3) : "memory");
}
__device__ __forceinline__ void prefetch_map(const CUtensorMap* m) {
  asm volatile("prefetch.tensormap [%0];" ::"l"(m) : "memory");
}
__device__ __forceinline__ void fence_async() { asm volatile("fence.proxy.async.global;" ::: "memory"); }
__device__ __forceinline__ void fence_async_smem() { asm volatile("fence.proxy.async.shared::cta;" ::: "memory"); }
__device__ __forceinline__ void bar_sync(int id, int n) { asm volatile("bar.sync %0, %1;" ::"r"(id), "r"(n) : "memory"); }
__device__ __forceinline__ void bar_arrive(int id, int n) { asm volatile("bar.arrive %0, %1;" ::"r"(id), "r"(n) : "memory"); }
__device__ __forceinline__ void wg_fence() { asm volatile("wgmma.fence.sync.aligned;" ::: "memory"); }
__device__ __forceinline__ void wg_commit() { asm volatile("wgmma.commit_group.sync.aligned;" ::: "memory"); }
template <int N> __device__ __forceinline__ void wg_wait() { asm volatile("wgmma.wait_group.sync.aligned %0;" ::"n"(N) : "memory"); }
__device__ __forceinline__ uint64_t make_desc(uint32_t addr, uint32_t lbo, uint32_t sbo) {
  return (uint64_t)((addr & 0x3FFFF) >> 4) | ((uint64_t)(lbo >> 4) << 16) | ((uint64_t)(sbo >> 4) << 32) | (1ull << 62);
}
__device__ __forceinline__ uint32_t ld_relaxed(const uint32_t* p) {
  uint32_t v; asm volatile("ld.relaxed.gpu.global.u32 %0, [%1];" : "=r"(v) : "l"(p) : "memory"); return v;
}
__device__ __forceinline__ uint32_t ld_acquire(const uint32_t* p) {
  uint32_t v; asm volatile("ld.acquire.gpu.global.u32 %0, [%1];" : "=r"(v) : "l"(p) : "memory"); return v;
}
__device__ __forceinline__ uint4 ld_relaxed4(const uint32_t* p) {
  uint4 v; asm volatile("ld.relaxed.gpu.global.v4.u32 {%0,%1,%2,%3}, [%4];" : "=r"(v.x), "=r"(v.y), "=r"(v.z), "=r"(v.w) : "l"(p) : "memory"); return v;
}
__device__ __forceinline__ void st_relaxed(uint32_t* p, uint32_t v) {
  asm volatile("st.relaxed.gpu.global.u32 [%0], %1;" ::"l"(p), "r"(v) : "memory");
}
__device__ __forceinline__ void st_relaxed4(uint32_t* p, uint32_t a, uint32_t b, uint32_t c, uint32_t d) {
  asm volatile("st.relaxed.gpu.global.v4.u32 [%0], {%1,%2,%3,%4};" ::"l"(p), "r"(a), "r"(b), "r"(c), "r"(d) : "memory");
}
__device__ __forceinline__ void st_b128(uint32_t* p, uint32_t a, uint32_t b, uint32_t c, uint32_t d) {
  asm volatile("{ .reg .b64 u, v; .reg .b128 w; mov.b64 u, {%1, %2}; mov.b64 v, {%3, %4}; mov.b128 w, {u, v}; st.relaxed.gpu.global.b128 [%0], w; }"
               ::"l"(p), "r"(a), "r"(b), "r"(c), "r"(d) : "memory");
}
__device__ __forceinline__ uint4 ld_b128(const uint32_t* p) {
  uint4 r;
  asm volatile("{ .reg .b64 u, v; .reg .b128 w; ld.relaxed.gpu.global.b128 w, [%4]; mov.b128 {u, v}, w; mov.b64 {%0, %1}, u; mov.b64 {%2, %3}, v; }"
               : "=r"(r.x), "=r"(r.y), "=r"(r.z), "=r"(r.w) : "l"(p) : "memory");
  return r;
}
__device__ __forceinline__ void st_pairs(uint32_t* p, uint32_t a, uint32_t b, uint32_t tag) {
  asm volatile("{ .reg .b64 u, v; mov.b64 u, {%1, %3}; mov.b64 v, {%2, %3}; st.relaxed.gpu.global.v2.b64 [%0], {u, v}; }"
               ::"l"(p), "r"(a), "r"(b), "r"(tag) : "memory");
}
__device__ __forceinline__ uint4 ld_pairs(const uint32_t* p) {
  uint4 v;
  asm volatile("{ .reg .b64 u, v; ld.relaxed.gpu.global.v2.b64 {u, v}, [%4]; mov.b64 {%0, %1}, u; mov.b64 {%2, %3}, v; }"
               : "=r"(v.x), "=r"(v.y), "=r"(v.z), "=r"(v.w) : "l"(p) : "memory");
  return v;
}
__device__ __forceinline__ uint2 ld_pair(const uint32_t* p) {
  uint2 v;
  asm volatile("{ .reg .b64 u; ld.relaxed.gpu.global.b64 u, [%2]; mov.b64 {%0, %1}, u; }" : "=r"(v.x), "=r"(v.y) : "l"(p) : "memory");
  return v;
}
__device__ __forceinline__ void red_release(uint32_t* p, uint32_t v) {
  asm volatile("red.release.gpu.global.add.u32 [%0], %1;" ::"l"(p), "r"(v) : "memory");
}
__device__ __forceinline__ uint32_t ldg_nc1(const void* p) {
  uint32_t v;
  asm volatile("ld.global.nc.u32 %0, [%1];" : "=r"(v) : "l"(p));
  return v;
}
__device__ __forceinline__ uint4 ldg_nc4(const void* p) {
  uint4 v; asm volatile("ld.global.nc.L1::no_allocate.v4.u32 {%0,%1,%2,%3}, [%4];" : "=r"(v.x), "=r"(v.y), "=r"(v.z), "=r"(v.w) : "l"(p)); return v;
}
__device__ __forceinline__ uint4 ldg_stream4(const void* p) {
  uint4 v;
  asm volatile("ld.global.nc.L1::no_allocate.L2::cache_hint.v4.u32 {%0,%1,%2,%3}, [%4], %5;" : "=r"(v.x), "=r"(v.y), "=r"(v.z), "=r"(v.w) : "l"(p), "l"(l2_stream()));
  return v;
}
__device__ __forceinline__ void stg4(void* p, uint4 v) {
  asm volatile("st.global.v4.u32 [%0], {%1,%2,%3,%4};" ::"l"(p), "r"(v.x), "r"(v.y), "r"(v.z), "r"(v.w) : "memory");
}
__device__ __forceinline__ void wait_counter(const uint32_t* p, uint32_t target) {
  uint32_t n = 0;
  while (__any_sync(0xffffffffu, (int)(ld_acquire(p) - target) < 0)) { watchdog(n); }
}
__device__ __forceinline__ uint32_t tagf(float v, uint32_t tag) { return (__float_as_uint(v) & ~3u) | tag; }
__device__ __forceinline__ bool tag_ok(uint4 v, uint32_t tag) { return (((v.x ^ tag) | (v.y ^ tag) | (v.z ^ tag) | (v.w ^ tag)) & 3u) == 0; }
__device__ __forceinline__ float untag_sum(uint32_t a, uint32_t b) { return __uint_as_float(a & ~3u) + __uint_as_float(b & ~3u); }
__device__ __forceinline__ uint4 poll4(const uint32_t* p, uint32_t tag) {
  uint4 v = ld_relaxed4(p);
  uint32_t n = 0;
  while (!__all_sync(0xffffffffu, tag_ok(v, tag))) { v = ld_relaxed4(p); watchdog(n); }
  return v;
}
__device__ __forceinline__ float bf_lo(uint32_t v) { return __uint_as_float(v << 16); }
__device__ __forceinline__ float bf_hi(uint32_t v) { return __uint_as_float(v & 0xffff0000u); }
__device__ __forceinline__ uint32_t pack_bf(float lo, float hi) {
  uint32_t r; asm("cvt.rn.bf16x2.f32 %0, %1, %2;" : "=r"(r) : "f"(hi), "f"(lo)); return r;
}
__device__ __forceinline__ float rbf(float v) { return __uint_as_float(pack_bf(0.f, v) & 0xffff0000u); }
__device__ __forceinline__ uint32_t hmul2(uint32_t a, uint32_t b) {
  uint32_t r; asm("mul.rn.bf16x2 %0, %1, %2;" : "=r"(r) : "r"(a), "r"(b)); return r;
}
__device__ __forceinline__ uint32_t hadd2(uint32_t a, uint32_t b) {
  uint32_t r; asm("add.rn.bf16x2 %0, %1, %2;" : "=r"(r) : "r"(a), "r"(b)); return r;
}
__device__ __forceinline__ uint32_t hsub2(uint32_t a, uint32_t b) {
  uint32_t r; asm("sub.rn.bf16x2 %0, %1, %2;" : "=r"(r) : "r"(a), "r"(b)); return r;
}
__device__ __forceinline__ float rcp(float x) { float r; asm("rcp.approx.ftz.f32 %0, %1;" : "=f"(r) : "f"(x)); return r; }
__device__ __forceinline__ float ex2(float x) { float r; asm("ex2.approx.ftz.f32 %0, %1;" : "=f"(r) : "f"(x)); return r; }
__device__ __forceinline__ void stmatrix4(uint32_t addr, uint32_t a, uint32_t b, uint32_t c, uint32_t d) {
  asm volatile("stmatrix.sync.aligned.m8n8.x4.shared.b16 [%0], {%1,%2,%3,%4};" ::"r"(addr), "r"(a), "r"(b), "r"(c), "r"(d) : "memory");
}
__device__ __forceinline__ void ldmatrix4(uint32_t addr, uint32_t& a, uint32_t& b, uint32_t& c, uint32_t& d) {
  asm volatile("ldmatrix.sync.aligned.m8n8.x4.shared.b16 {%0,%1,%2,%3}, [%4];" : "=r"(a), "=r"(b), "=r"(c), "=r"(d) : "r"(addr) : "memory");
}
__device__ __forceinline__ void ldmatrix4t(uint32_t addr, uint32_t& a, uint32_t& b, uint32_t& c, uint32_t& d) {
  asm volatile("ldmatrix.sync.aligned.m8n8.x4.trans.shared.b16 {%0,%1,%2,%3}, [%4];" : "=r"(a), "=r"(b), "=r"(c), "=r"(d) : "r"(addr) : "memory");
}
__device__ __forceinline__ void mma16816(float (&d)[4], uint32_t a0, uint32_t a1, uint32_t a2, uint32_t a3, uint32_t b0, uint32_t b1) {
  asm volatile("mma.sync.aligned.m16n8k16.row.col.f32.bf16.bf16.f32 {%0,%1,%2,%3}, {%4,%5,%6,%7}, {%8,%9}, {%0,%1,%2,%3};"
               : "+f"(d[0]), "+f"(d[1]), "+f"(d[2]), "+f"(d[3]) : "r"(a0), "r"(a1), "r"(a2), "r"(a3), "r"(b0), "r"(b1));
}
__device__ __forceinline__ void sts1(uint32_t a, uint32_t v) { asm volatile("st.shared.u32 [%0], %1;" ::"r"(a), "r"(v) : "memory"); }
__device__ __forceinline__ uint4 lds4(uint32_t a) {
  uint4 v; asm volatile("ld.shared.v4.u32 {%0,%1,%2,%3}, [%4];" : "=r"(v.x), "=r"(v.y), "=r"(v.z), "=r"(v.w) : "r"(a) : "memory"); return v;
}
__device__ __forceinline__ uint2 lds2(uint32_t a) {
  uint2 v; asm volatile("ld.shared.v2.u32 {%0,%1}, [%2];" : "=r"(v.x), "=r"(v.y) : "r"(a) : "memory"); return v;
}
__device__ __forceinline__ uint32_t lds1(uint32_t a) {
  uint32_t v; asm volatile("ld.shared.u32 %0, [%1];" : "=r"(v) : "r"(a) : "memory"); return v;
}
__device__ __forceinline__ void sts2(uint32_t a, uint32_t x, uint32_t y) { asm volatile("st.shared.v2.u32 [%0], {%1,%2};" ::"r"(a), "r"(x), "r"(y) : "memory"); }
__device__ __forceinline__ void sts4(uint32_t a, uint4 v) {
  asm volatile("st.shared.v4.u32 [%0], {%1,%2,%3,%4};" ::"r"(a), "r"(v.x), "r"(v.y), "r"(v.z), "r"(v.w) : "memory");
}
__device__ __forceinline__ float silu_f(float v) { return __fdividef(v, 1.f + __expf(-v)); }
__device__ __forceinline__ uint32_t hfma2(uint32_t a, uint32_t b, uint32_t c) {
  uint32_t r; asm("fma.rn.bf16x2 %0, %1, %2, %3;" : "=r"(r) : "r"(a), "r"(b), "r"(c)); return r;
}
__device__ __forceinline__ void split_inv(float sd, uint32_t& ih, uint32_t& il) {
  const float inv = rcp(sd);
  ih = pack_bf(inv, inv);
  const float lo = inv - bf_lo(ih);
  il = pack_bf(lo, lo);
}
__device__ __forceinline__ uint32_t ln_norm(uint32_t x, uint32_t mean2, uint32_t ih, uint32_t il) {
  const uint32_t d = hsub2(x, mean2);
  return hfma2(d, ih, hmul2(d, il));
}
__device__ __forceinline__ uint32_t ln_mod(uint32_t x, uint32_t mean2, uint32_t ih, uint32_t il, uint32_t c1, uint32_t sh) {
  return hadd2(hmul2(ln_norm(x, mean2, ih, il), c1), sh);
}

#define R8(a, i) "+f"(a[i]), "+f"(a[i + 1]), "+f"(a[i + 2]), "+f"(a[i + 3]), "+f"(a[i + 4]), "+f"(a[i + 5]), "+f"(a[i + 6]), "+f"(a[i + 7])
#define D64 "{%0,%1,%2,%3,%4,%5,%6,%7,%8,%9,%10,%11,%12,%13,%14,%15,%16,%17,%18,%19,%20,%21,%22,%23,%24,%25,%26,%27,%28,%29,%30,%31," \
            "%32,%33,%34,%35,%36,%37,%38,%39,%40,%41,%42,%43,%44,%45,%46,%47,%48,%49,%50,%51,%52,%53,%54,%55,%56,%57,%58,%59,%60,%61,%62,%63}"
template <int TB>
__device__ __forceinline__ void mma_ss(float (&d)[64], uint64_t da, uint64_t db, int sc) {
  asm volatile("{\n.reg .pred p;\nsetp.ne.b32 p, %66, 0;\n"
               "wgmma.mma_async.sync.aligned.m64n128k16.f32.bf16.bf16 " D64 ", %64, %65, p, 1, 1, 0, %67;\n}"
               : R8(d, 0), R8(d, 8), R8(d, 16), R8(d, 24), R8(d, 32), R8(d, 40), R8(d, 48), R8(d, 56)
               : "l"(da), "l"(db), "r"(sc), "n"(TB));
}
template <int TB>
__device__ __forceinline__ void mma_rs(float (&d)[64], uint32_t a0, uint32_t a1, uint32_t a2, uint32_t a3, uint64_t db, int sc) {
  asm volatile("{\n.reg .pred p;\nsetp.ne.b32 p, %69, 0;\n"
               "wgmma.mma_async.sync.aligned.m64n128k16.f32.bf16.bf16 " D64 ", {%64,%65,%66,%67}, %68, p, 1, 1, %70;\n}"
               : R8(d, 0), R8(d, 8), R8(d, 16), R8(d, 24), R8(d, 32), R8(d, 40), R8(d, 48), R8(d, 56)
               : "r"(a0), "r"(a1), "r"(a2), "r"(a3), "l"(db), "r"(sc), "n"(TB));
}
#define D128 "{%0,%1,%2,%3,%4,%5,%6,%7,%8,%9,%10,%11,%12,%13,%14,%15,%16,%17,%18,%19,%20,%21,%22,%23,%24,%25,%26,%27,%28,%29,%30,%31," \
             "%32,%33,%34,%35,%36,%37,%38,%39,%40,%41,%42,%43,%44,%45,%46,%47,%48,%49,%50,%51,%52,%53,%54,%55,%56,%57,%58,%59,%60,%61,%62,%63," \
             "%64,%65,%66,%67,%68,%69,%70,%71,%72,%73,%74,%75,%76,%77,%78,%79,%80,%81,%82,%83,%84,%85,%86,%87,%88,%89,%90,%91,%92,%93,%94,%95," \
             "%96,%97,%98,%99,%100,%101,%102,%103,%104,%105,%106,%107,%108,%109,%110,%111,%112,%113,%114,%115,%116,%117,%118,%119,%120,%121,%122,%123,%124,%125,%126,%127}"
#define R128(d, e) R8(d, 0), R8(d, 8), R8(d, 16), R8(d, 24), R8(d, 32), R8(d, 40), R8(d, 48), R8(d, 56), \
                   R8(e, 0), R8(e, 8), R8(e, 16), R8(e, 24), R8(e, 32), R8(e, 40), R8(e, 48), R8(e, 56)
__device__ __forceinline__ void mma256_ss(float (&d)[64], float (&e)[64], uint64_t da, uint64_t db, int sc) {
  asm volatile("{\n.reg .pred p;\nsetp.ne.b32 p, %130, 0;\n"
               "wgmma.mma_async.sync.aligned.m64n256k16.f32.bf16.bf16 " D128 ", %128, %129, p, 1, 1, 0, 1;\n}"
               : R128(d, e) : "l"(da), "l"(db), "r"(sc));
}
__device__ __forceinline__ void mma256_rs(float (&d)[64], float (&e)[64], uint32_t a0, uint32_t a1, uint32_t a2, uint32_t a3, uint64_t db) {
  asm volatile("{\n.reg .pred p;\nsetp.ne.b32 p, 1, 0;\n"
               "wgmma.mma_async.sync.aligned.m64n256k16.f32.bf16.bf16 " D128 ", {%128,%129,%130,%131}, %132, p, 1, 1, 1;\n}"
               : R128(d, e) : "r"(a0), "r"(a1), "r"(a2), "r"(a3), "l"(db));
}
template <int N> __device__ __forceinline__ void keep(float (&a)[N]) {
#pragma unroll
  for (int i = 0; i < N; i++) asm volatile("" : "+f"(a[i])::"memory");
}
template <int N> __device__ __forceinline__ void keep(uint32_t (&a)[N]) {
#pragma unroll
  for (int i = 0; i < N; i++) asm volatile("" : "+r"(a[i])::"memory");
}

#define STAMP(idx) do {} while (0)
#define PROF(grp, cond, idx) do {} while (0)

constexpr float SCL2 = 1.4426950408889634f * 0.08838834764831845f;

__device__ __forceinline__ void pack_p(const float (&s)[64], uint32_t (&p)[32]) {
#pragma unroll
  for (int i = 0; i < 32; i++) p[i] = pack_bf(s[2 * i], s[2 * i + 1]);
}

__device__ __forceinline__ void issue_qk(float (&s)[64], uint32_t q0, uint32_t q1, uint32_t kslot) {
  const uint64_t db = make_desc(kslot, 16, 1024), da0 = make_desc(q0, 16, 1024), da1 = make_desc(q1, 16, 1024);
#pragma unroll
  for (int kk = 0; kk < 8; kk++) mma_ss<0>(s, (kk < 4 ? da0 : da1) + (kk & 3) * 2, db + (kk >> 2) * 1024 + (kk & 3) * 2, kk != 0);
}
__device__ __forceinline__ void issue_pv(float (&o)[64], uint32_t (&p)[32], uint32_t vslot, int acc) {
  uint64_t db = make_desc(vslot, 16384, 1024);
#pragma unroll
  for (int kk = 0; kk < 8; kk++)
    mma_rs<1>(o, p[4 * kk], p[4 * kk + 1], p[4 * kk + 2], p[4 * kk + 3], db + kk * 128, kk == 0 ? acc : 1);
}

template <int H>
__device__ __forceinline__ void store_chunk(const float (&a)[64], uint32_t addr) {
#pragma unroll
  for (int i = 8 * H; i < 8 * H + 8; i += 2)
    stmatrix4(addr ^ ((i & 7) << 4), pack_bf(a[4 * i], a[4 * i + 1]), pack_bf(a[4 * i + 2], a[4 * i + 3]),
              pack_bf(a[4 * i + 4], a[4 * i + 5]), pack_bf(a[4 * i + 6], a[4 * i + 7]));
}
template <int H>
__device__ __forceinline__ void store_chunk(const float (&a)[64], float i0, float i1, uint32_t addr) {
#pragma unroll
  for (int i = 8 * H; i < 8 * H + 8; i += 2)
    stmatrix4(addr ^ ((i & 7) << 4), pack_bf(a[4 * i] * i0, a[4 * i + 1] * i0), pack_bf(a[4 * i + 2] * i1, a[4 * i + 3] * i1),
              pack_bf(a[4 * i + 4] * i0, a[4 * i + 5] * i0), pack_bf(a[4 * i + 6] * i1, a[4 * i + 7] * i1));
}
__device__ __forceinline__ float inv_quad_sum(float l) {
  l += __shfl_xor_sync(0xffffffffu, l, 1);
  l += __shfl_xor_sync(0xffffffffu, l, 2);
  return rcp(l);
}

__device__ __forceinline__ void write_table(uint32_t table, bool ca, uint32_t t, const uint4& m0, const uint4& m1) {
  float c0 = untag_sum(m0.x, m1.x), c1 = untag_sum(m0.y, m1.y), c2 = untag_sum(m0.z, m1.z), c3 = untag_sum(m0.w, m1.w);
  if (ca) { c0 = 1.f + rbf(c0); c1 = 1.f + rbf(c1); c2 = 1.f + rbf(c2); c3 = 1.f + rbf(c3); }
  const uint32_t d = table + (t >> 2) * 64 + (t & 1) * 32 + (t & 2) * 2 + (ca ? 0 : 8);
  sts1(d, pack_bf(c0, c1));
  sts1(d + 16, pack_bf(c2, c3));
}

__device__ __forceinline__ void ln_scalars(float mean, float var, float& mb, float& sd) {
  mb = rbf(mean);
  float r; asm("sqrt.approx.ftz.f32 %0, %1;" : "=f"(r) : "f"(rbf(rbf(var) + 1e-5f)));
  sd = rbf(r);
}

__global__ void __cluster_dims__(2, 1, 1) __launch_bounds__(384, 1) fused_kernel(const __grid_constant__ Maps maps, const Ptrs P) {
  extern __shared__ __align__(1024) uint8_t smem_raw[];
  const uint32_t base = smem_u32(smem_raw);
  const int tid = threadIdx.x, lane = tid & 31;
  const int warp = __shfl_sync(0xffffffffu, tid >> 5, 0);
  int b = blockIdx.x;
  if (b < NMAIN) {
    const int p = b >> 1;
    const int grp = p < 4 ? 7 : (p < 36 ? (p + 2) & 7 : (p - 30) % 7), k = p < 4 ? 4 + p : (p < 36 ? (p - 4) >> 3 : 4 + (p - 36) / 7);
    b = grp << 4 | k << 1 | (b & 1);
  }
  PROF(31, tid == 0, 0);

  if (b >= NMAIN) {
    float* sc = reinterpret_cast<float*>(smem_raw);
    float* red = sc + DM;
    for (int k = tid; k < DM; k += 384) sc[k] = rbf(silu_f(__bfloat162float(P.c[k])));
    __syncthreads();
    if (tid < 256) {
      const int col = 2048 + (b - NMAIN) * 1024 + (tid & 127) * 8, r0 = (tid >> 7) * 512;
      float acc[8];
#pragma unroll
      for (int e = 0; e < 8; e++) acc[e] = 0.f;
#pragma unroll 1
      for (int r = r0; r < r0 + 512; r += HU) {
        uint4 w[HU];
#pragma unroll
        for (int u = 0; u < HU; u++) w[u] = ldg_stream4(P.w_mod + (size_t)(r + u) * NMOD + col);
#pragma unroll
        for (int u = 0; u < HU; u++) {
          float s = sc[r + u];
          acc[0] += s * bf_lo(w[u].x); acc[1] += s * bf_hi(w[u].x); acc[2] += s * bf_lo(w[u].y); acc[3] += s * bf_hi(w[u].y);
          acc[4] += s * bf_lo(w[u].z); acc[5] += s * bf_hi(w[u].z); acc[6] += s * bf_lo(w[u].w); acc[7] += s * bf_hi(w[u].w);
        }
      }
      if (tid >= 128) {
#pragma unroll
        for (int e = 0; e < 8; e++) red[(tid & 127) * 8 + e] = acc[e];
      }
      const uint32_t tag = ld_relaxed(&g_epoch) % 3 + 1;
      bar_sync(1, 256);
      if (tid < 128) {
        uint32_t o[8];
#pragma unroll
        for (int e = 0; e < 8; e++) o[e] = __float_as_uint(rbf(acc[e] + red[tid * 8 + e])) | tag;
        st_relaxed4(g_mod + col, o[0], o[1], o[2], o[3]);
        st_relaxed4(g_mod + col + 4, o[4], o[5], o[6], o[7]);
        const uint4 wr = ldg_nc4(P.w_r + tid * 8);
        const uint32_t wv[4] = {wr.x, wr.y, wr.z, wr.w};
        float dsum = 0.f;
#pragma unroll
        for (int e = 0; e < 8; e++) {
          const float m = bf_hi(o[e]);
          dsum += (b == NMAIN + 2 ? rbf(1.f + m) : m) * ((e & 1) ? bf_hi(wv[e >> 1]) : bf_lo(wv[e >> 1]));
        }
#pragma unroll
        for (int k = 16; k > 0; k >>= 1) dsum += __shfl_xor_sync(0xffffffffu, dsum, k);
        if (lane == 0) st_relaxed(g_mod + (b - NMAIN) * 4 + warp, tagf(dsum, tag));
      }
    }
    PROF(2, tid == 0, 1);
    return;
  }

  const int rank = b & 1;
  const int rb = ((b >> 4) << 1) | rank, cj = (b >> 1) & 7;
  const bool late = b & 4;
  const uint32_t bfull = base + OFF_BAR, bempty = bfull + NSLOT * 8;
  const uint32_t gfull = bempty + NSLOT * 8, gempty = gfull + 32;
  const uint32_t bar_ofull = gempty + 32;
  const uint32_t bar_ofree = bar_ofull + 32;
  const uint32_t bar_par = bar_ofree + 32;
  const uint32_t bar_mod = bar_par + 8;
  const uint32_t bar_pread = bar_mod + 8;
  const uint32_t bar_xres = bar_pread + 8;
  const uint32_t bar_ring = bar_xres + 8;
  const uint32_t bar_box = bar_ring + 24;
  const uint32_t bar_go = bar_box + 96;
  const uint32_t bar_go2 = bar_go + 16;
  const uint32_t bar_cnt = bar_go + 24;
  const uint32_t xfull = bar_go + 40, xempty = xfull + 32;
  const uint32_t bar_hw = xempty + 32, bar_hx = bar_hw + 8;
  const uint32_t bar_hpub = bar_hx + 16;
  const uint32_t bar_win = bar_hpub + 16;
  const uint32_t bar_rx = bar_win + 8;
  const uint32_t bar_sel = bar_rx + 8;
  const uint32_t bar_gate = bar_sel + 8;
  const uint32_t bar_rel = bar_gate + 8;
  const uint32_t bar_od = bar_rel + 8;
  const uint32_t bar_mod2 = bar_od + 8;
  const uint32_t bar_res = bar_go + 8;
  const uint32_t stage = base + OFF_STAGE, par = base + OFF_PAR;

  if (warp == 10 && elect_one()) prefetch_map(&maps.wm);
  if (warp == 8 && elect_one()) {
    for (int s = 0; s < NSLOT; s++) { mbar_init(bfull + s * 8, 1); mbar_init(bempty + s * 8, 16); }
    for (int s = 0; s < 4; s++) { mbar_init(gfull + s * 8, 1); mbar_init(gempty + s * 8, 16); mbar_init(xfull + s * 8, 1); mbar_init(xempty + s * 8, 8); mbar_init(bar_ofree + s * 8, 1); mbar_init(bar_ofull + s * 8, 128); }
    mbar_init(bar_par, 64); mbar_init(bar_mod, 256); mbar_init(bar_pread, 2); mbar_init(bar_xres, 1);
    mbar_init(bar_ring, 8); mbar_init(bar_ring + 8, 8); mbar_init(bar_ring + 16, 8);
    mbar_init(bar_go, 1); mbar_init(bar_go2, 1); mbar_init(bar_cnt, 1); mbar_init(bar_cnt + 8, 1); mbar_init(bar_hpub, 8); mbar_init(bar_hpub + 8, 8); mbar_init(bar_res, 1); mbar_init(bar_win, 1); mbar_init(bar_rx, 1); mbar_init(bar_sel, 64); mbar_init(bar_gate, 8); mbar_init(bar_rel, 8); mbar_init(bar_od, 1); mbar_init(bar_mod2, 64);
    for (int s = 0; s < 12; s++) mbar_init(bar_box + s * 8, 1);
    asm volatile("fence.mbarrier_init.release.cluster;" ::: "memory");
    prefetch_map(&maps.x); prefetch_map(&maps.wq); prefetch_map(&maps.k); prefetch_map(&maps.v);
  }
  if (warp == 9 && elect_one()) {
    mbar_init(bar_hw, 1); mbar_init(bar_hx, 1); mbar_init(bar_hx + 8, 1);
    asm volatile("fence.mbarrier_init.release.cluster;" ::: "memory");
    mbar_expect_tx(bar_hw, 32768);
    mbar_expect_tx(bar_hx, 16384);
    mbar_expect_tx(bar_hx + 8, 16384);
    const __nv_bfloat16* xs = P.x + (size_t)(rb * 128 + cj * 16) * DM;
    bulk_load(base + 2 * GST_BYTES, xs, 16384, bar_hx);
    if (!late) {
      tma2d(stage, &maps.wm, (b >> 1) * 32, rank * 512, bar_hw);
      tma2d(stage + 16384, &maps.wm, (b >> 1) * 32, rank * 512 + 256, bar_hw);
    }
    bulk_load(base + 3 * GST_BYTES, xs + 8 * DM, 16384, bar_hx + 8);
  }
  cluster_arrive();

  if (warp >= 8) {
    asm volatile("setmaxnreg.dec.sync.aligned.u32 40;");
    if (warp < 10) bar_arrive(1, 320);
    const uint32_t epoch = ld_relaxed(&g_epoch);
    cluster_wait();
    if (warp == 8) {
      const int kvrow = (cj >> 1) * SK + (SK - WIN);
      int wch = cj * 8 + rank * 2;
#pragma unroll 1
      for (int ps = 0; ps < 3; ps++) {
        const CUtensorMap* mw = ps == 2 ? &maps.wo : &maps.wq;
        const uint32_t xt = ps == 1 ? XT1 : XT2, wt = ps == 0 ? WT0 : (ps == 1 ? WT1 : WT2);
        const int nst = ps == 2 ? 32 : 16;
#pragma unroll 1
        for (int i = 0; i < nst; i++) {
          const uint32_t bf = gfull + (i & 3) * 8;
          const int kt = ps == 2 ? (((cj & 1) * 4 + ((i >> 1) & 3)) * 4 + (i >> 3)) * 2 + (i & 1) : (ps ? i : slice_of(i) + (b & 14)) & 15;
          const uint32_t wd = base + unit_of(wt, i & 3) + rank * UNIT, xd = base + unit_of(xt, i & 3);
          const uint8_t* xs = g_act + (uint32_t)(rb * 80 + (ps - 1) * 16 + kt) * UNIT;
          if (ps == 0 && i == HD) mbar_wait(bar_mod, 0);
          if (ps == 2 && (i & 7) == 0 && i != 8) mbar_wait(i ? bar_cnt + i - 16 : bar_ofree + 24, 0);
          if ((i & 7) == 0) fence_async();
          if (i == RES0) mbar_wait(bar_res, 0);
          mbar_wait(bf, ((i >> 2) & 1) ^ 1);
          if (elect_one()) {
            mbar_expect_tx(bf, ps ? GST_BYTES : 2 * UNIT);
            if (ps && i < 2) bulk_load_stream(xd, xs, UNIT, bf);
            mbar_arrive_pred(bar_go, i == GOST);
            mbar_arrive_pred(bar_go2, ps == 1 && i == PG0);
            mbar_arrive_pred(bar_od, ps && i == (ps == 1 ? ODS1 : ODS) + 1);
            if (i == RES0) mbar_expect_tx(bar_xres, 32768);
          }
          const int wk = (i == 31 ? kt ^ (rank * 32) : kt) * 64, wc = i == 31 ? cj * 2 : wch;
          const uint64_t xp = i == 31 ? l2_normal() : l2_stream();
          mbar_wait(ps && i < 4 ? bempty + i * 8 : gempty + (i & 3) * 8, ((i >> 2) & 1) ^ 1);
          if (elect_one()) {
            tma3d_mc<true>(wd, mw, 0, wk, wc, bf);
            if (ps && i > 2) bulk_load_stream(xd, xs, UNIT, bf, xp);
            if (i == RES0 || i == RES1) tma2d(base + OFF_RES + (i == RES1) * UNIT, &maps.x, cj * 128 + (i == RES1) * 64, rb * 128, bar_xres);
          }
          if (ps && i == 2) {
            mbar_wait(bar_ofree + (ps - 1) * 16, 0);
            if (elect_one()) bulk_load_stream(xd, xs, UNIT, bf);
          }
        }
        if (ps == 2) break;
        wch = ps ? ((wch >> 3) ^ rank) * 2 : wch + 4;
#pragma unroll 1
        for (int u = 0; u < 16; u++) {
          const bool isk = (u == 0) || ((u & 1) && u < 15), kept = (0x1680 >> u) & 1;
          const int blk = (0x472FAD84u >> (u * 2)) & 3;
          const uint32_t sl = base + unit_of(ps ? AT1 : AT0, u & 3) + rank * UNIT, bf = bfull + (u & 3) * 8;
          mbar_wait(bf, ((u >> 2) & 1) ^ 1);
          if (!kept && elect_one()) mbar_expect_tx(bf, SLOT_BYTES);
          mbar_wait(u < 4 ? gempty + ((u + 1) >> 1) * 8 : bempty + (u & 3) * 8, ((u >> 2) & 1) ^ 1);
          if (elect_one()) {
            if (kept) mbar_arrive(bf);
            else if (ps && (blk >= 2 || u > 8)) tma3d_mc<true>(sl, isk ? &maps.k : &maps.v, 0, kvrow + blk * 128, rank, bf);
            else tma3d_mc<false>(sl, isk ? &maps.k : &maps.v, 0, kvrow + blk * 128, rank, bf);
          }
        }
      }
      if (elect_one()) mbar_expect_tx(bar_rx, UNIT);
      mbar_wait(bar_rel, 0);
      if (elect_one()) {
        bulk_load_stream(base + UNIT, g_act + (uint32_t)(rb * 80 + 16 + 63 - (cj & 1) * 32) * UNIT, UNIT, bar_rx);
      }
      if (b < NFFN) {
#pragma unroll 1
        for (int u = 0; u < 12; u++) {
          const uint32_t dst = base + unit_of(u < 4 ? FT_G : (u < 8 ? FT_U : FT_D), u & 3);
          if (elect_one()) mbar_expect_tx(bar_box + u * 8, UNIT);
          if (u == 0 || u == 2 || u == 8) mbar_wait(bar_ring + (u == 8 ? 16 : u * 4), 0);
          const int fp = u < 8 ? FPACE0 : FPACE;
          if (u >= fp) mbar_wait(bar_box + (u - fp) * 8, 0);
          if (elect_one()) {
            if (u < 8) tma2d(dst, u < 4 ? &maps.wg : &maps.wu, b * 32, (u & 3) * 256, bar_box + u * 8);
            else tma3d(dst, &maps.wd, 0, b * 32, (u - 8) * 4, bar_box + u * 8);
          }
        }
      }
    } else if (warp == 9) {
      const uint32_t target = 8 * (epoch + 1);
      uint32_t hmask = 0;
#pragma unroll 1
      for (int i = 0; i < 16; i++) {
        if (i == HDX) mbar_wait(bar_mod, 0);
        const int kt = (2 * cj + slice_of(i)) & 15;
        const uint32_t need = i == 15 ? 0xffffu : 1u << kt;
        if (i >= NRS && (hmask & need) != need) {
          uint32_t n = 0;
          do { hmask = __ballot_sync(0xffffffffu, ld_acquire(&g_cnt_h[rb * 32 + (lane & 15)]) == epoch + 1); watchdog(n); } while ((hmask & need) != need);
          PROF(1, lane == 0 && i == NRS, 26);
          fence_async();
        }
        mbar_wait(xempty + (i & 3) * 8, ((i >> 2) & 1) ^ 1);
        if (elect_one()) {
          mbar_expect_tx(xfull + (i & 3) * 8, UNIT);
          if (i < NRS) tma2d(base + (i & 3) * GST_BYTES, &maps.x, kt * 64, rb * 128, xfull + (i & 3) * 8);
          else bulk_load_stream(base + (i & 3) * GST_BYTES, g_act + (uint32_t)(rb * 80 + kt) * UNIT, UNIT, xfull + (i & 3) * 8);
        }
      }
      prefetch_map(&maps.wo);
#pragma unroll 1
      for (int t = 0; t < 4; t++) {
        if (t & 1) mbar_wait(bar_od, t >> 1);
        const int ops = OPS >> (t & 1);
#pragma unroll 1
        for (int p = 0; p < 32768; p += ops) {
          const uint32_t w = p >> 14, c = (p >> 13) & 1, off = w * 8192 + (p & 8191);
          mbar_wait(bar_ofull + (t & 1) * 16 + w * 8, t >> 1);
          if (elect_one()) {
            bulk_store(g_act + (uint32_t)(rb * 80 + 16 + (cj * 4 + t) * 2 + c) * UNIT + off, base + unit_of(QT, 2 * t + c) + off, ops);
            asm volatile("cp.async.bulk.commit_group;" ::: "memory");
            asm volatile("cp.async.bulk.wait_group.read 0;" ::: "memory");
          }
        }
        if (elect_one()) {
          mbar_arrive(t < 3 ? bar_ofree + t * 8 : bar_res);
          asm volatile("cp.async.bulk.wait_group 0;" ::: "memory");
          fence_async();
          red_release(&g_cnt_o[((rb * 4 + t) * 2 + (cj >> 2)) * 32], 2);
        }
        if (t) {
          wait_counter(&g_cnt_o[(rb * 8 + 2 * t + (cj & 1)) * 32], target);
          if (t & 1) wait_counter(&g_cnt_o[(rb * 8 + (t == 1 ? cj & 1 : 7 - (cj & 1))) * 32], target);
          if (elect_one()) mbar_arrive(t == 1 ? bar_ofree + 24 : bar_cnt + t * 8 - 16);
        }
      }
      PROF(2, lane == 0, 27);
      const uint32_t tag = epoch % 3 + 1;
      const uint32_t* inbox = g_cand + (b >> 4) % CR * 512 + (lane & 15) * CS;
      mbar_wait(bar_ring + 16, 0);
      uint32_t c0 = ld_relaxed(inbox), n = 0;
#define CAND_STEP(cv)                                                                                        \
      {                                                                                                      \
        const bool valid = (cv & 3u) == tag, all = __all_sync(0xffffffffu, valid);                           \
        const uint32_t best = __reduce_max_sync(0xffffffffu, valid ? cv : 0u);                               \
        const uint32_t blk = __ffs(__ballot_sync(0xffffffffu, cv == best)) - 1;                              \
        if (best) sts2(par + PAR_CONST + 56, best, (blk << 7 | (~best >> 2 & 127)) | (all ? 0x1800 : 0x800)); \
        if (all) break;                                                                                      \
        cv = ld_relaxed(inbox);                                                                              \
      }
      while (true) { CAND_STEP(c0) watchdog(n); }
    } else {
      const int t2 = tid - 320;
      if (late && warp == 10) {
        mbar_wait(bar_hx + HWB * 8, 0);
        if (elect_one()) {
          tma2d(stage, &maps.wm, (b >> 1) * 32, rank * 512, bar_hw);
          tma2d(stage + 16384, &maps.wm, (b >> 1) * 32, rank * 512 + 256, bar_hw);
        }
      }
      {
        const uint32_t tag = epoch % 3 + 1;
        mbar_wait(bar_hx + 8, 0);
        mbar_wait(bar_hw, 0);
        __nanosleep(late ? OSL2 : OSL);
        {
          const uint32_t t7 = (warp & 1) * 64 + (lane >> 4) * 32 + 16 + (lane & 15);
          const uint32_t* pm = g_modp + ((cj * 128 + t7 * 4) & (DM - 1));
          uint4 m0, m1, m2, m3;
          uint32_t n = 0;
          do {
            m0 = ld_relaxed4(pm); m1 = ld_relaxed4(pm + 2 * DM); m2 = ld_relaxed4(pm + DM); m3 = ld_relaxed4(pm + 3 * DM);
            watchdog(n);
          } while (!__all_sync(0xffffffffu, tag_ok(m0, tag) && tag_ok(m1, tag) && tag_ok(m2, tag) && tag_ok(m3, tag)));
          write_table(par, false, t7, m0, m1);
          write_table(par, true, t7, m2, m3);
          mbar_arrive(bar_mod2);
        }
      }
      mbar_wait(bar_hpub + (warp & 1) * 8, 0);
      PROF(1, t2 == 0, 24);
#pragma unroll 1
      for (int c = 0; c < 8; c++) {
        const uint32_t off = (warp & 1) * UNIT + c * 2048 + lane * 16;
        uint8_t* dst = g_act + (uint32_t)(rb * 80 + cj * 2) * UNIT + off;
        const uint4 v0 = lds4(stage + off), v1 = lds4(stage + off + 512), v2 = lds4(stage + off + 1024), v3 = lds4(stage + off + 1536);
        stg4(dst, v0); stg4(dst + 512, v1); stg4(dst + 1024, v2); stg4(dst + 1536, v3);
      }
      __syncwarp();
      PROF(1, t2 == 0, 15);
      if (lane == 0) {
        mbar_arrive(bar_pread);
        red_release(&g_cnt_h[rb * 32 + cj * 2 + (warp & 1)], 1);
        PROF(1, t2 == 0, 25);
        prefetch_map(&maps.wg); prefetch_map(&maps.wu); prefetch_map(&maps.wd); prefetch_map(&maps.out);
      }
      __syncwarp();
      if (b < NFFN) {
        mbar_wait(bar_go2, 0);
        const __nv_bfloat16* pg = ((b & 1) ? P.w_up : P.w_gate) + (b >> 1) * 64 + (size_t)t2 * FF;
        const __nv_bfloat16* pd = P.w_down + (size_t)b * 32768 + t2 * 64;
        PROF(2, t2 == 0, 13);
#pragma unroll 1
        for (int i = 0; i < WN; i += WB) {
          uint32_t v[WB];
#pragma unroll
          for (int u = 0; u < WB; u++) {
            const int k = i + u;
            asm volatile("ld.global.cg.L2::128B.u32 %0, [%1];" : "=r"(v[u]) : "l"(k < 16 ? pg + (size_t)k * 64 * FF : pd + (k - 16) * 4096));
          }
#pragma unroll
          for (int u = 1; u < WB; u++) v[0] ^= v[u];
          sts1(par + PAR_SINK + t2 * 4, v[0]);
        }
        PROF(2, t2 == 0, 14);
      }
      const uint32_t tag = epoch % 3 + 1;
      mbar_wait(bar_go, 0);
      bar_sync(4, 64);
      if (warp == 10) {
        const uint32_t* src = g_mod + 2 * DM + cj * 128 + lane * 4;
        const uint2 wr = *reinterpret_cast<const uint2*>(P.w_r + cj * 128 + lane * 4);
        uint4 vga, vsb, vcb, vgb;
        uint32_t n = 0;
        do {
          vga = ld_relaxed4(src); vsb = ld_relaxed4(src + DM); vcb = ld_relaxed4(src + 2 * DM); vgb = ld_relaxed4(src + 3 * DM);
          watchdog(n);
        } while (!__all_sync(0xffffffffu, tag_ok(vga, tag) && tag_ok(vsb, tag) && tag_ok(vcb, tag) && tag_ok(vgb, tag)));
        const float c0 = rbf(1.f + bf_hi(vcb.x)), c1 = rbf(1.f + bf_hi(vcb.y)), c2 = rbf(1.f + bf_hi(vcb.z)), c3 = rbf(1.f + bf_hi(vcb.w));
        const float a0 = c0 * bf_lo(wr.x), a1 = c1 * bf_hi(wr.x), a2 = c2 * bf_lo(wr.y), a3 = c3 * bf_hi(wr.y);
        const uint32_t h0 = pack_bf(a0, a1), h1 = pack_bf(a2, a3);
        const uint32_t t1 = par + PAR_T1 + (lane >> 2) * 64 + (lane & 1) * 32 + (lane & 2) * 2;
        sts1(t1, h0); sts1(t1 + 8, pack_bf(a0 - bf_lo(h0), a1 - bf_hi(h0)));
        sts1(t1 + 16, h1); sts1(t1 + 24, pack_bf(a2 - bf_lo(h1), a3 - bf_hi(h1)));
        const uint32_t tg = par + PAR_SINK + (lane >> 3) * 64 + (lane & 1) * 32 + (lane & 6) * 2;
        sts1(tg, __byte_perm(vga.x, vga.y, 0x7632)); sts1(tg + 16, __byte_perm(vga.z, vga.w, 0x7632));
        sts4(par + PAR_T2 + lane * 32, make_uint4(pack_bf(c0, c1), __byte_perm(vsb.x, vsb.y, 0x7632), __byte_perm(vgb.x, vgb.y, 0x7632), __byte_perm(vga.x, vga.y, 0x7632)));
        sts4(par + PAR_T2 + lane * 32 + 16, make_uint4(pack_bf(c2, c3), __byte_perm(vsb.z, vsb.w, 0x7632), __byte_perm(vgb.z, vgb.w, 0x7632), __byte_perm(vga.z, vga.w, 0x7632)));
      } else {
        const uint4 g = poll4((lane & 8) ? g_mod + 8 - (lane & 1) * 4 : g_mod + 5 * DM + (b >> 4) * 128 + (lane & 7) * 16 + (b & 12), tag);
        sts1(par + PAR_CONST + 60, 0);
        if (lane < 8) sts1(par + PAR_CONST + 16 + lane * 4, (b & 2) ? ((b & 1) ? g.w : g.z) : ((b & 1) ? g.y : g.x));
        else if (lane < 10) sts2(par + PAR_CONST + (lane - 8) * 8, __float_as_uint(untag_sum(g.x, g.y) + untag_sum(g.z, g.w)), epoch);
      }
      __syncwarp();
#pragma unroll 1
      for (int q = 0; q < 32; q++) {
        st_b128(g_xch + ((size_t)b * 8 * 256 + q * 64 + t2) * 4, (epoch & 1) << 16, 0, 0, 0);
        __nanosleep(RSL);
      }
      for (int q = 0; q < 2; q++) st_relaxed4(g_stats + (((rb * 8 + q * 4 + (t2 >> 4)) * 8 + cj) * 16 + (t2 & 15)) * 4, 0, 0, 0, 0);
      if (b < NFFN)
        for (int q = 0; q < 2; q++) st_relaxed4(ypart_slot(b, q * 64 + t2), 0, 0, 0, 0);
      st_relaxed4(g_row + rb * 2 * DM + (t2 >> 5) * DM + cj * 128 + (t2 & 31) * 4, 0, 0, 0, 0);
      __threadfence();
      mbar_arrive(bar_par);
      mbar_wait(bar_gate, 0);
      uint32_t have = 0, n = 0;
      while (true) {
        const uint32_t st = lds1(par + PAR_CONST + 60) >> 7;
        if ((st & 31) != have) {
          const uint32_t* hsrc = g_row + (st & 15) * 2 * DM + t2 * 4;
          uint4 hv[4];
          bool ok = true;
#pragma unroll
          for (int i = 0; i < 4; i++) hv[i] = ld_pairs(hsrc + i * 256);
#pragma unroll
          for (int i = 0; i < 4; i++) {
            sts2(base + ((FT_G >> i * 4) & 15) * UNIT + (warp & 1) * 8192 + 256 + lane * 8, hv[i].x, hv[i].z);
            ok = ok && hv[i].y == tag && hv[i].w == tag;
          }
          have = __all_sync(0xffffffffu, ok) ? st & 31 : 0;
        }
        if ((st ^ have) == 32) break;
        watchdog(n);
      }
      mbar_arrive(bar_sel);
    }
    __syncwarp();
    cluster_arrive();
    {
      const uint32_t tag = epoch % 3 + 1, t3 = tid - 256;
      mbar_wait(bar_win, 0);
      uint2 win = lds2(par + PAR_CONST + 56);
      win.y &= 0x7ff;
      const uint32_t* fsrc = g_row + (win.y >> 7) * 2 * DM + (b >> 4) * 128 + (t3 & 7) * 16 + (b & 6) * 2 + ((b >> 2) & 2);
      const uint32_t* ysrc = ypart_slot(min(t3, NFFN - 1), b);
      uint2 fh = ld_pair(fsrc), fx = ld_pair(fsrc + DM);
      uint4 ya = ld_b128(ysrc);
      const float rwin = __uint_as_float(((int)win.x < 0 ? win.x & 0x7fffffffu : ~win.x) & ~0x1ffu);
      const float rs = rbf(rcp(1.f + __expf(-rbf(rwin))));
      uint32_t n = 0;
      while (__any_sync(0xffffffffu, fh.y != tag || fx.y != tag)) { fh = ld_pair(fsrc); fx = ld_pair(fsrc + DM); watchdog(n); }
      while (true) {
        const bool miss = ((ya.x & 1) | (ya.y & 1) << 1) != tag;
        if (!__any_sync(0xffffffffu, miss)) break;
        if (miss) ya = ld_b128(ysrc);
        watchdog(n);
      }
      PROF(8, t3 == 0, 5);
      float y[8] = {bf_lo(ya.x & ~1u), bf_hi(ya.x), bf_lo(ya.y & ~1u), bf_hi(ya.y), bf_lo(ya.z), bf_hi(ya.z), bf_lo(ya.w), bf_hi(ya.w)};
#pragma unroll
      for (int h = 4; h > 0; h >>= 1) {
        const bool up = lane & (h * 2);
#pragma unroll
        for (int e = 0; e < h; e++) y[e] = (up ? y[e + h] : y[e]) + __shfl_xor_sync(0xffffffffu, up ? y[e] : y[e + h], h * 2);
      }
      y[0] += __shfl_xor_sync(0xffffffffu, y[0], 1);
      if (!(lane & 1)) sts1(par + PAR_RED + 64 + t3 * 2, __float_as_uint(y[0]));
      bar_sync(4, 128);
      if (t3 < 8) {
        float y0 = 0.f;
#pragma unroll
        for (int w7 = 0; w7 < 7; w7++) y0 += __uint_as_float(lds1(par + PAR_RED + 64 + w7 * 32 + t3 * 4));
        const uint32_t gv = lds1(par + PAR_CONST + 16 + t3 * 4);
        const uint32_t upd = hmul2(pack_bf(y0, y0), pack_bf(rs, rs));
        const uint32_t r = hadd2(fx.x, hmul2(__byte_perm(gv, gv, 0x3232), hadd2(fh.x, upd)));
        reinterpret_cast<uint16_t*>(P.out)[(size_t)win.y * DM + (b >> 4) * 128 + t3 * 16 + (b & 15)] = (b & 1) ? r >> 16 : r;
        if (b == 0 && t3 == 0) st_relaxed(&g_epoch, epoch + 1);
      }
      PROF(31, t3 == 0, 36);
    }
    cluster_wait();
  } else {
    const int wg = warp >> 2;

    uint32_t tag;
    auto gemv = [&]() {
      const uint32_t l = fresh_lane(), fr = (l & 7) + (l >> 4) * 8, tq = l & 3, row = base + 2 * GST_BYTES + warp * 2048;
      const uint32_t wa = stage + warp * 4096 + fr * 64 + ((((l >> 3) & 1) ^ ((fr >> 1) & 3)) << 4);
      uint32_t sc[8];
#pragma unroll
      for (int k = 0; k < 8; k++) sc[k] = lds1(row + 128 + k * 16 + tq * 4);
      float d0[4] = {0.f, 0.f, 0.f, 0.f}, d1[4] = {0.f, 0.f, 0.f, 0.f};
      mbar_wait(bar_hw, 0);
#pragma unroll
      for (int ks = 0; ks < 4; ks++) {
        uint32_t w[8];
        ldmatrix4t(wa + ks * 1024, w[0], w[1], w[2], w[3]);
        ldmatrix4t((wa ^ 32) + ks * 1024, w[4], w[5], w[6], w[7]);
        mma16816(d0, w[0], w[1], w[2], w[3], sc[2 * ks], sc[2 * ks + 1]);
        mma16816(d1, w[4], w[5], w[6], w[7], sc[2 * ks], sc[2 * ks + 1]);
      }
      sts1(row + (tq * 8 + (l >> 2)) * 4, __float_as_uint((tq & 2) ? ((tq & 1) ? d1[2] : d1[0]) : ((tq & 1) ? d0[2] : d0[0])));
      bar_sync(1, 256);
      if (warp == 0) {
        float s = 0.f;
#pragma unroll
        for (int w8 = 0; w8 < 8; w8++) s += __uint_as_float(lds1(row + w8 * 2048 + l * 4));
        st_relaxed(g_modp + rank * 2 * DM + (b >> 1) * 32 + l, (__float_as_uint(s) & ~3u) | tag);
      }
      PROF(1, tid == 0, 3);
    };
    {
      uint32_t* const pmod = g_modp + rank * 2 * DM + (b >> 1) * 32 + lane;
      uint32_t* const pln = g_ln1 + (rb * 128 + cj * 16 + warp) * 4;
      const uint32_t cv = ldg_nc1(P.c + rank * 512 + tid * 2);
      const uint32_t epoch = ld_relaxed(&g_epoch);
      if (warp == 0) st_relaxed(pmod, 0);
      if (lane == 0) { st_b128(pln, 0, 0, 0, 0); st_b128(pln + 32, 0, 0, 0, 0); }
      asm volatile("setmaxnreg.inc.sync.aligned.u32 232;");
      bar_sync(1, 320);
      tag = epoch % 3 + 1;
#pragma unroll
      for (int part = 0; part < 3; part++) {
        if (!(part & 1)) {
          const uint32_t xa = base + (2 + part / 2) * GST_BYTES + warp * 2048 + lane * 16;
          mbar_wait(bar_hx + part * 4, 0);
          float s0 = 0.f, s1 = 0.f, q0 = 0.f, q1 = 0.f;
#pragma unroll
          for (int q = 0; q < 4; q++) {
            const uint4 xv = lds4(xa + q * 512);
            const uint32_t u[4] = {xv.x, xv.y, xv.z, xv.w};
#pragma unroll
            for (int e = 0; e < 4; e++) { const float lo = bf_lo(u[e]), hi = bf_hi(u[e]); s0 += lo; s1 += hi; q0 += lo * lo; q1 += hi * hi; }
          }
          s0 += s1; q0 += q1;
#pragma unroll
          for (int o = 16; o > 0; o >>= 1) { s0 += __shfl_xor_sync(0xffffffffu, s0, o); q0 += __shfl_xor_sync(0xffffffffu, q0, o); }
          const float mean = s0 * (1.f / DM);
          float mb, sd;
          ln_scalars(mean, fmaxf(q0 * (1.f / DM) - mean * mean, 0.f), mb, sd);
          uint32_t ih, il;
          split_inv(sd, ih, il);
          if (lane == 0) st_b128(pln + part * 16, pack_bf(mb, mb), ih, il, tag);
          PROF(1, tid == 0 && part == 2, 4);
        } else {
          __syncwarp();
          sts1(base + 2 * GST_BYTES + warp * 2048 + 128 + lane * 4, pack_bf(silu_f(bf_lo(cv)), silu_f(bf_hi(cv))));
          __syncwarp();
          if (!late) gemv();
        }
      }
      cluster_wait();
      if (wg == 1) bar_arrive(2, 256);
    }

    const uint32_t rempty = lane < 2 ? mapa(bempty, lane & 1) : 0;
    constexpr uint32_t GE = NSLOT * 8 + 32;
    float o[64], s[64];
#pragma unroll 1
    for (int ps = 0; ps < 3; ps++) {
      {
        const uint32_t xt = ps == 1 ? XT1 : XT2, wt = ps == 1 ? WT1 : WT2;
        const int nst = ps == 2 ? 28 : 14;
        if (ps == 0) {
          float ga[64], gb[64];
#pragma unroll
          for (int i = 0; i < 64; i++) { ga[i] = 0.f; gb[i] = 0.f; }
          uint32_t a[2][16];
          const uint32_t l = fresh_lane();
          uint32_t fa[4];
#pragma unroll
          for (int kk = 0; kk < 4; kk++) fa[kk] = (base + wg * 8192 + frag_offset(warp)) ^ (kk * 32);
          const uint32_t mt = par + (l & 3) * 16;
          auto fetch = [&](int i, uint32_t (&f)[16], uint32_t z) {
            mbar_wait(xfull + (i & 3) * 8, i >> 2);
#pragma unroll
            for (int kk = 0; kk < 4; kk++) ldmatrix4(fa[kk] + (i & 3) * GST_BYTES + z, f[4 * kk], f[4 * kk + 1], f[4 * kk + 2], f[4 * kk + 3]);
          };
          const bool oddw = warp & 2;
          uint4 r0, r1;
          {
            const uint32_t t7 = (warp & 1) * 64 + (l >> 4) * 32 + (l & 15);
            const uint32_t* pm = g_modp + wg * DM + ((cj * 128 + t7 * 4) & (DM - 1));
            const uint32_t* pr = g_ln1 + (rb * 128 + warp * 16 + (l >> 2)) * 4;
            uint4 m0 = make_uint4(tag, tag, tag, tag), m1 = m0;
            if (GL == 0 && late) gemv();
            if (GL == 2) { fetch(0, a[0], 0); fetch(1, a[1], 0); }
            mbar_wait(bar_hw, 0);
            if (!oddw) { m0 = ld_relaxed4(pm); m1 = ld_relaxed4(pm + 2 * DM); }
            r0 = ld_b128(pr); r1 = ld_b128(pr + 32);
            if (GL && late) gemv();
            if (GL != 2) { fetch(0, a[0], 0); fetch(1, a[1], 0); }
            uint32_t n = 0;
            bool written = false;
#pragma unroll 1
            while (true) {
              uint32_t miss;
              asm volatile("{ .reg .pred p0, p1, p2, p3; .reg .b32 t, u;\n"
                           "lop3.b32 t, %1, %2, %19, 0x7e; lop3.b32 u, %3, %4, %19, 0x7e; or.b32 t, t, u; and.b32 t, t, 3; setp.ne.u32 p0, t, 0;\n"
                           "lop3.b32 t, %5, %6, %19, 0x7e; lop3.b32 u, %7, %8, %19, 0x7e; or.b32 t, t, u; and.b32 t, t, 3; setp.ne.u32 p1, t, 0;\n"
                           "setp.ne.u32 p2, %12, %19; setp.ne.u32 p3, %16, %19;\n"
                           "@p0 ld.relaxed.gpu.global.v4.u32 {%1, %2, %3, %4}, [%17];\n"
                           "@p1 ld.relaxed.gpu.global.v4.u32 {%5, %6, %7, %8}, [%17 + 8192];\n"
                           "@p2 ld.relaxed.gpu.global.v4.u32 {%9, %10, %11, %12}, [%18];\n"
                           "@p3 ld.relaxed.gpu.global.v4.u32 {%13, %14, %15, %16}, [%18 + 128];\n"
                           "or.pred p0, p0, p1; or.pred p2, p2, p3; vote.sync.any.pred p0, p0, 0xffffffff; vote.sync.any.pred p2, p2, 0xffffffff;\n"
                           "selp.u32 t, 1, 0, p0; selp.u32 u, 2, 0, p2; or.b32 %0, t, u; }"
                           : "=r"(miss), "+r"(m0.x), "+r"(m0.y), "+r"(m0.z), "+r"(m0.w), "+r"(m1.x), "+r"(m1.y), "+r"(m1.z), "+r"(m1.w),
                             "+r"(r0.x), "+r"(r0.y), "+r"(r0.z), "+r"(r0.w), "+r"(r1.x), "+r"(r1.y), "+r"(r1.z), "+r"(r1.w)
                           : "l"(pm), "l"(pr), "r"(tag) : "memory");
              if (!(miss & 1) && !written) {
                written = true;
                if (!oddw) write_table(par, wg, t7, m0, m1);
                mbar_arrive(bar_mod);
              }
              if (!miss) break;
              watchdog(n);
            }
          }
          const uint32_t zero = r0.w ^ tag;
          auto normalize = [&](uint32_t (&f)[16]) {
#pragma unroll
            for (int k = 0; k < 16; k += 2) { f[k] = ln_norm(f[k], r0.x, r0.y, r0.z); f[k + 1] = ln_norm(f[k + 1], r1.x, r1.y, r1.z); }
          };
          auto modulate = [&](int i, uint32_t (&f)[16]) {
#pragma unroll
            for (int kk = 0; kk < 4; kk++) {
              const uint4 m = lds4(mt + slice_of(i) * 256 + kk * 64);
              f[4 * kk] = hfma2(f[4 * kk], m.x, m.z); f[4 * kk + 1] = hfma2(f[4 * kk + 1], m.x, m.z);
              f[4 * kk + 2] = hfma2(f[4 * kk + 2], m.y, m.w); f[4 * kk + 3] = hfma2(f[4 * kk + 3], m.y, m.w);
            }
            keep(f);
            mbar_arrive_pred(xempty + (i & 3) * 8, l == 0);
          };
          auto publish = [&](int u, uint32_t (&f)[16]) {
#pragma unroll
            for (int kk = 0; kk < 4; kk++) stmatrix4(fa[kk] + OFF_STAGE + u * UNIT, f[4 * kk], f[4 * kk + 1], f[4 * kk + 2], f[4 * kk + 3]);
            __syncwarp();
            mbar_arrive_pred(bar_hpub + u * 8, l == 0);
          };
          auto multiply = [&](int i, uint32_t (&f)[16]) {
            mbar_wait(gfull + (i & 3) * 8, i >> 2);
            const uint64_t db = make_desc(base + (i & 3) * GST_BYTES + UNIT, 8192, 1024);
            wg_fence();
#pragma unroll
            for (int kk = 0; kk < 4; kk++) mma256_rs(ga, gb, f[4 * kk], f[4 * kk + 1], f[4 * kk + 2], f[4 * kk + 3], db + kk * 128);
            wg_commit();
          };
          auto next = [&](int i, uint32_t (&f)[16]) {
            wg_wait<1>();
            mbar_arrive_cl(rempty, GE + ((i + 2) & 3) * 8);
            uint32_t z = zero;
#pragma unroll
            for (int k = 0; k < 16; k += 2) asm volatile("lop3.b32 %0, %1, %2, %0, 0xA8;" : "+r"(z) : "r"(f[k]), "r"(f[k + 1]));
            fetch(i, f, z);
            normalize(f);
            if (i == OST) { keep(f); mbar_wait(bar_mod2, 0); }
            modulate(i, f); multiply(i, f);
          };
          normalize(a[0]);
          keep(a[0]); keep(a[1]);
          mbar_wait(bar_mod, 0);
          PROF(1, tid == 0, 2);
          modulate(0, a[0]); multiply(0, a[0]); publish(0, a[0]);
          keep(a[1]);
          normalize(a[1]);
          modulate(1, a[1]); multiply(1, a[1]);
#pragma unroll 1
          for (int i = 2; i < NRS; i += 2) {
            next(i, a[0]);
            if (!(OST & 1) && i == OST) publish(1, a[0]);
            next(i + 1, a[1]);
            if ((OST & 1) && i + 1 == OST) publish(1, a[1]);
          }
          wg_wait<1>();
          mbar_arrive_cl(rempty, GE + ((NRS + 2) & 3) * 8);
#pragma unroll 1
          for (int i = NRS; i < 14; i++) {
            mbar_wait(xfull + (i & 3) * 8, (i >> 2) & 1);
            mbar_wait(gfull + (i & 3) * 8, (i >> 2) & 1);
            const uint32_t xa = base + (i & 3) * GST_BYTES;
            const uint64_t da = make_desc(xa + wg * 8192, 16, 1024), db = make_desc(xa + UNIT, 8192, 1024);
            if (i == 13) bar_sync(2 + wg, 256);
            wg_fence();
#pragma unroll
            for (int kk = 0; kk < 4; kk++) mma256_ss(ga, gb, da + kk * 2, db + kk * 128, 1);
            wg_commit();
            if (i == 13) bar_arrive(3 - wg, 256);
            wg_wait<1>();
            uint32_t z = zero;
#pragma unroll
            for (int k = 0; k < 16; k += 2) asm volatile("lop3.b32 %0, %1, %2, %0, 0xA8;" : "+r"(z) : "r"(a[1][k]), "r"(a[1][k + 1]));
            mbar_arrive_cl(rempty, GE + ((i + 3) & 3) * 8 + z);
            mbar_arrive_pred(xempty + ((i + 3) & 3) * 8, l == 0 && i != NRS);
          }
          mbar_wait(xfull + 16, 1);
          wg_wait<0>();
          keep(ga); keep(gb);
#pragma unroll
          for (int i = 0; i < 64; i++) {
            asm volatile("mov.b32 %0, %1;" : "=f"(s[i]) : "f"(ga[i]));
            asm volatile("mov.b32 %0, %1;" : "=f"(o[i]) : "f"(gb[i]));
          }
        } else {
          float ga[64], gb[64];
#pragma unroll
          for (int i = 0; i < 64; i++) {
            asm volatile("mov.b32 %0, %1;" : "=f"(ga[i]) : "f"(s[i]));
            asm volatile("mov.b32 %0, %1;" : "=f"(gb[i]) : "f"(o[i]));
          }
#pragma unroll 1
          for (int i = 0; i < nst; i++) {
            mbar_wait(gfull + (i & 3) * 8, (i >> 2) & 1);
            const uint64_t da = make_desc(base + unit_of(xt, i & 3) + wg * 8192, 16, 1024), db = make_desc(base + unit_of(wt, i & 3), 8192, 1024);
            if (i == nst - 1) bar_sync(2 + wg, 256);
            wg_fence();
#pragma unroll
            for (int kk = 0; kk < 4; kk++) mma256_ss(ga, gb, da + kk * 2, db + kk * 128, kk ? 1 : i);
            wg_commit();
            if (i == nst - 1) bar_arrive(3 - wg, 256);
            wg_wait<1>();
            mbar_arrive_cl(rempty, GE + ((i + 3) & 3) * 8, i != 0);
            PROF(4, tid == 0 && (i & 3) == 0, 40 + (ps - 1) * 4 + i / 4);
          }
          wg_wait<0>();
          keep(ga); keep(gb);
#pragma unroll
          for (int i = 0; i < 64; i++) {
            asm volatile("mov.b32 %0, %1;" : "=f"(s[i]) : "f"(ga[i]));
            asm volatile("mov.b32 %0, %1;" : "=f"(o[i]) : "f"(gb[i]));
          }
        }
        mbar_arrive_cl(rempty, GE + (ps == 2 ? 24 : 8));
        if (ps == 2) break;
      }
      const uint32_t qw = base + wg * 8192, qt = QT >> (16 * ps), at = ps ? AT1 : AT0;
      {
        const uint32_t wt = ps ? WT1 : WT0;
        const uint64_t da0 = make_desc(qw + unit_of(qt, 2), 16, 1024), da1 = make_desc(qw + unit_of(qt, 3), 16, 1024);
        const uint64_t db0 = make_desc(base + unit_of(wt, 2), 8192, 1024), db1 = make_desc(base + unit_of(wt, 3), 8192, 1024);
        mbar_wait(gfull + 16, 1);
        bar_sync(2 + wg, 256);
        wg_fence();
#pragma unroll
        for (int kk = 0; kk < 4; kk++) mma_ss<1>(s, da0 + kk * 2, db0 + kk * 128, 1);
        wg_commit();
        mbar_wait(xfull + 24, 1);
        mbar_wait(gfull + 24, 1);
        wg_fence();
#pragma unroll
        for (int kk = 0; kk < 4; kk++) mma_ss<1>(s, da1 + kk * 2, db1 + kk * 128, 1);
        wg_commit();
        bar_arrive(3 - wg, 256);
        mbar_wait(ps == 0 ? bar_pread : bar_ofree + 8, 0);
        wg_wait<0>();
        keep(s);
        PROF(2, tid == 0, 8 + ps * 8);
        uint32_t q[32];
        pack_p(s, q);
#pragma unroll
        for (int i = 0; i < 4; i++) stmatrix4((qw + unit_of(qt, 0) + frag_offset(warp)) ^ (i << 5), q[4 * i], q[4 * i + 1], q[4 * i + 2], q[4 * i + 3]);
        keep(q);
        bar_sync(2 + wg, 256);
        wg_fence();
#pragma unroll
        for (int kk = 0; kk < 8; kk++) mma_ss<1>(o, (kk < 4 ? da0 : da1) + (kk & 3) * 2, (kk < 4 ? db0 : db1) + UNIT / 16 + (kk & 3) * 128, 1);
        wg_commit();
        mbar_wait(bfull, 0);
        wg_fence();
        const uint64_t dk = make_desc(base + unit_of(at, 0), 16, 1024);
#pragma unroll
        for (int kk = 0; kk < 8; kk++) mma_rs<0>(s, q[4 * kk], q[4 * kk + 1], q[4 * kk + 2], q[4 * kk + 3], dk + (kk >> 2) * 1024 + (kk & 3) * 2, kk != 0);
        wg_commit();
        bar_arrive(3 - wg, 256);
#pragma unroll
        for (int i = 4; i < 8; i++) stmatrix4((qw + unit_of(qt, 1) + frag_offset(warp)) ^ ((i & 3) << 5), q[4 * i], q[4 * i + 1], q[4 * i + 2], q[4 * i + 3]);
        wg_wait<1>();
        keep(o);
        mbar_arrive_cl(rempty, GE + 16);
        mbar_arrive_cl(rempty, GE + 24);
        store_chunk<0>(o, qw + unit_of(qt, 2) + frag_offset(warp));
        store_chunk<1>(o, qw + unit_of(qt, 3) + frag_offset(warp));
        wg_wait<0>();
        keep(s);
        mbar_arrive_cl(rempty, 0);
      }
      PROF(4, tid == 0 && ps == 1, 61);
      float l0 = 0.f, l1 = 0.f, f0 = 0.f, f1 = 0.f;
      auto step = [&](auto odd_c, const int j, uint32_t (&pw)[32], uint32_t (&pr)[32]) {
        constexpr bool ODD = decltype(odd_c)::value;
        const bool first = !ODD && (j & 2) == 0, last = ODD && j == 7;
        const uint32_t ph = (j >> 1) & 1;
        float i0, i1, a0, a1;
        const bool so = !ODD && j == 4;
        if (so) { i0 = inv_quad_sum(l0); i1 = inv_quad_sum(l1); l0 = 0.f; l1 = 0.f; }
        if (first) {
          int m0 = max(__float_as_int(s[0]), __float_as_int(s[1])), m1 = max(__float_as_int(s[2]), __float_as_int(s[3]));
#pragma unroll
          for (int i = 1; i < 16; i++) {
            m0 = __vimax3_s32(m0, __float_as_int(s[4 * i]), __float_as_int(s[4 * i + 1]));
            m1 = __vimax3_s32(m1, __float_as_int(s[4 * i + 2]), __float_as_int(s[4 * i + 3]));
          }
          m0 = max(m0, __shfl_xor_sync(0xffffffffu, m0, 1)); m1 = max(m1, __shfl_xor_sync(0xffffffffu, m1, 1));
          m0 = max(m0, __shfl_xor_sync(0xffffffffu, m0, 2)); m1 = max(m1, __shfl_xor_sync(0xffffffffu, m1, 2));
          f0 = fmaf(__int_as_float(m0), SCL2, BIAS); f1 = fmaf(__int_as_float(m1), SCL2, BIAS);
        }
        bool redo = false;
        while (true) {
          if (redo) {
            float m0 = fmaxf(s[0], s[1]), m1 = fmaxf(s[2], s[3]);
#pragma unroll
            for (int i = 1; i < 16; i++) { m0 = fmaxf(m0, fmaxf(s[4 * i], s[4 * i + 1])); m1 = fmaxf(m1, fmaxf(s[4 * i + 2], s[4 * i + 3])); }
            m0 = fmaxf(m0, __shfl_xor_sync(0xffffffffu, m0, 1)); m1 = fmaxf(m1, __shfl_xor_sync(0xffffffffu, m1, 1));
            m0 = fmaxf(m0, __shfl_xor_sync(0xffffffffu, m0, 2)); m1 = fmaxf(m1, __shfl_xor_sync(0xffffffffu, m1, 2));
            m0 = fmaf(m0, SCL2, BIAS); m1 = fmaf(m1, SCL2, BIAS);
            if (!first) {
              m0 = fmaxf(m0, f0); m1 = fmaxf(m1, f1);
              const float c0 = ex2(f0 - m0), c1 = ex2(f1 - m1);
              l0 *= c0; l1 *= c1;
              wg_wait<0>();
              keep(o);
#pragma unroll
              for (int i = 0; i < 16; i++) { o[4 * i] *= c0; o[4 * i + 1] *= c0; o[4 * i + 2] *= c1; o[4 * i + 3] *= c1; }
            }
            f0 = m0; f1 = m1;
          }
          float b0 = 0.f, b1 = 0.f;
          a0 = 0.f; a1 = 0.f;
#pragma unroll
          for (int i = 0; i < 16; i++) {
            const float e0 = ex2(fmaf(s[4 * i], SCL2, -f0)), e1 = ex2(fmaf(s[4 * i + 1], SCL2, -f0));
            const float e2 = ex2(fmaf(s[4 * i + 2], SCL2, -f1)), e3 = ex2(fmaf(s[4 * i + 3], SCL2, -f1));
            a0 += e0; b0 += e1; a1 += e2; b1 += e3;
            pw[2 * i] = pack_bf(e0, e1); pw[2 * i + 1] = pack_bf(e2, e3);
            if (i == VREL) {
#pragma unroll
              for (int k = 0; k < 2 * VREL + 2; k++) asm volatile("" : "+r"(pw[k])::"memory");
              mbar_wait(bar_mod, 0);
              wg_wait<0>();
              mbar_arrive_cl(rempty, ODD ? 16 : 0, !redo && (ODD || j));
#pragma unroll
              for (int k = 4 * VREL + 4; k < 64; k++) asm volatile("" : "+f"(s[k])::"memory");
            }
          }
          a0 += b0; a1 += b1;
          if (redo) break;
          redo = __any_sync(0xffffffffu, !(a0 + a1 < 1.f));
          if (!redo) break;
        }
        l0 += a0; l1 += a1;
        keep(pw);
        keep(o);
        if (so) store_chunk<0>(o, i0, i1, qw + unit_of(qt, 0) + frag_offset(warp));
        keep(o);
        if (j == (ODD ? 5 : 0)) { fence_async_smem(); if (ODD) mbar_arrive(bar_ofull + wg * 8); }
        mbar_wait(bfull + (ODD ? 24 : 8), ph);
        bar_sync(2 + wg, 256);
        if (!last) {
          const uint32_t qn = qt >> (j >= 3 ? 8 : 0);
          wg_fence();
          issue_qk(s, qw + unit_of(qn, 0), qw + unit_of(qn, 1), base + unit_of(at, ODD ? 3 : 1));
          wg_commit();
          mbar_wait(bfull + (ODD ? 0 : 16), ODD ? ph ^ 1 : ph);
        }
        if (so) { store_chunk<1>(o, i0, i1, qw + unit_of(qt, 1) + frag_offset(warp)); keep(o); }
        wg_fence();
        issue_pv(o, pw, base + unit_of(at, ODD ? (last ? 3 : 0) : 2), !first);
        wg_commit();
        bar_arrive(3 - wg, 256);
        wg_wait<1>();
        keep(s);
        mbar_arrive_cl(rempty, ODD ? 24 : 8, !last);
        PROF(4, tid == 0 && ps == 1, 51 + j);
      };
      uint32_t pa[32], pb[32];
#pragma unroll 1
      for (int j = 0; j < 8; j += 2) {
        step(std::false_type{}, j, pa, pb);
        step(std::true_type{}, j + 1, pb, pa);
      }
      {
        const float i0 = inv_quad_sum(l0), i1 = inv_quad_sum(l1);
        wg_wait<0>();
        keep(o);
        mbar_arrive_cl(rempty, 24);
        store_chunk<0>(o, i0, i1, qw + unit_of(qt, 2) + frag_offset(warp));
        store_chunk<1>(o, i0, i1, qw + unit_of(qt, 3) + frag_offset(warp));
        fence_async_smem();
        mbar_arrive(bar_ofull + 16 + wg * 8);
      }
      PROF(2, tid == 0, 10 + ps * 8);
    }

    const int ln = fresh_lane(), g = ln >> 2, tq = ln & 3, ct = warp * 32 + ln;
    const bool lane0 = ln == 0;
    const int lrow0 = warp * 16 + g;
    const uint32_t res = base + OFF_RES, trow = res + wg * 8192 + frag_offset(warp);
    uint32_t xr[32];
    uint4 sv[4], own;
    uint32_t* const sg = g_stats + (rb * 8 + warp) * 512 + g * 4;
    uint32_t* sp[4];
#pragma unroll
    for (int k = 0; k < 4; k++) sp[k] = sg + (tq & 1) * 32 + (((tq >> 1) ^ (cj >> 2)) * 4 + (k ^ (cj & 3))) * 64;
    {
      const uint64_t da = make_desc(base + wg * 8192, 16, 1024), db = make_desc(base, 8192, 1024);
      constexpr int U = UNIT / 16;
#define HALF_STAGE(acc, xu, wu) _Pragma("unroll") for (int kk = 0; kk < 4; kk++) mma_ss<1>(acc, da + (xu) * U + kk * 2, db + (wu) * U + kk * 128, 1)
      PROF(10, ct == PT, 19); STAMP(0);
      cluster_arrive();
      mbar_wait(gfull, 1);
      mbar_wait(gfull + 8, 1);
      bar_sync(2 + wg, 256);
      wg_fence();
      HALF_STAGE(o, 7, 1);
      HALF_STAGE(o, 8, 3);
      wg_commit();
      STAMP(16);
      mbar_wait(gfull + 16, 1);
      STAMP(17);
      wg_fence();
      HALF_STAGE(o, 6, 11);
      wg_commit();
      bar_arrive(3 - wg, 256);
      mbar_wait(bar_par, 0);
      uint32_t* xo = g_xch + ((size_t)b * 8 * 256 + ct) * 4;
      const uint32_t* xi = g_xch + ((size_t)(b ^ 2) * 8 * 256 + ct) * 4;
      const uint32_t par1 = (~lds1(par + PAR_CONST + 4) & 1) << 16;
      wg_wait<1>();
      mbar_arrive_pred(bar_rel, lane0);
      wg_wait<0>();
      keep(o);
      mbar_arrive_pred(bar_ring, lane0);
      PROF(8, ct == PT, 20); STAMP(1);
#define SEND(i) st_b128(xo + (i) * 1024, (pack_bf(o[8 * (i)], o[8 * (i) + 1]) & ~0x10000u) | par1, pack_bf(o[8 * (i) + 2], o[8 * (i) + 3]), \
                        pack_bf(o[8 * (i) + 4], o[8 * (i) + 5]), pack_bf(o[8 * (i) + 6], o[8 * (i) + 7]))
#pragma unroll
      for (int i = 0; i < NS1; i++) SEND(i);
      PROF(8, ct == PT, 21); STAMP(2);
      bar_sync(2 + wg, 256);
      wg_fence();
      HALF_STAGE(s, 7, 0);
      HALF_STAGE(s, 8, 2);
      HALF_STAGE(s, 6, 10);
      wg_commit();
      bar_arrive(3 - wg, 256);
      STAMP(18);
      mbar_wait(gfull + 24, 1);
#pragma unroll
      for (int i = NS1; i < 8; i++) SEND(i);
      uint4 v[8];
      STAMP(19);
      mbar_wait(bar_xres, 0);
      wg_wait<0>();
      mbar_arrive_pred(bar_ring + 8, lane0);
      bar_sync(2 + wg, 256);
      STAMP(20);
#pragma unroll
      for (int i = 0; i < LD2; i++) v[i] = ld_b128(xi + i * 1024);
      mbar_wait(bar_xres, 0);
      wg_fence();
      HALF_STAGE(s, 9, 4);
      wg_commit();
      mbar_wait(bar_rx, 0);
      wg_fence();
      HALF_STAGE(s, 1, 5);
      wg_commit();
      bar_arrive(3 - wg, 256);
      STAMP(21);
#pragma unroll
      for (int i = LD2; i < 8; i++) v[i] = ld_b128(xi + i * 1024);
      mbar_wait(bar_xres, 0);
      wg_wait<0>();
      keep(s);
      mbar_arrive_pred(bar_ring + 16, lane0);
      PROF(10, ct == PT, 23); STAMP(4);
#pragma unroll
      for (int i = 0; i < 16; i += 2) ldmatrix4((trow ^ ((i & 7) << 4)) + (i >> 3) * 16384, xr[2 * i], xr[2 * i + 1], xr[2 * i + 2], xr[2 * i + 3]);
      uint32_t ga[16];
      uint4 bw[8];
#pragma unroll
      for (int i = 0; i < 8; i++) {
        if (!(i & 1)) {
          const uint4 t = lds4(par + PAR_SINK + i * 32 + tq * 16);
          ga[2 * i] = t.x; ga[2 * i + 1] = t.y; ga[2 * i + 2] = t.z; ga[2 * i + 3] = t.w;
        }
        bw[i] = lds4(par + PAR_T1 + i * 64 + tq * 16);
        if (!(g & 1)) { bw[i].x = 0x3f803f80u; bw[i].y = 0x3f803f80u; }
      }
      uint32_t pk[32];
      pack_p(s, pk);
      const uint32_t par2 = (~lds1(par + PAR_CONST + 12) & 1) << 16;
      {
        uint32_t n = 0, miss;
        do {
          miss = 0;
#pragma unroll
          for (int i = 0; i < 8; i++) miss |= v[i].x ^ par2;
          miss = __any_sync(0xffffffffu, miss & 0x10000u);
          if (miss) {
#pragma unroll
            for (int i = 0; i < 8; i++)
              asm volatile("{ .reg .pred p; .reg .b32 t; xor.b32 t, %0, %5; and.b32 t, t, 0x10000; setp.ne.u32 p, t, 0;\n"
                           "@p ld.relaxed.gpu.global.v4.u32 {%0, %1, %2, %3}, [%4]; }"
                           : "+r"(v[i].x), "+r"(v[i].y), "+r"(v[i].z), "+r"(v[i].w) : "l"(xi + i * 1024), "r"(par1) : "memory");
          }
          watchdog(n);
        } while (miss);
      }
      PROF(8, ct == PT, 22); STAMP(3);
      float ds[4] = {0.f, 0.f, 0.f, 0.f}, dl[4] = {0.f, 0.f, 0.f, 0.f}, q0[4] = {0.f, 0.f, 0.f, 0.f}, q1[4] = {0.f, 0.f, 0.f, 0.f};
#pragma unroll
      for (int i = 0; i < 8; i++) {
        const uint32_t u0 = hfma2(ga[2 * i], hadd2(pk[4 * i], v[i].x & ~0x10000u), xr[4 * i]);
        const uint32_t u1 = hfma2(ga[2 * i], hadd2(pk[4 * i + 1], v[i].y), xr[4 * i + 1]);
        const uint32_t u2 = hfma2(ga[2 * i + 1], hadd2(pk[4 * i + 2], v[i].z), xr[4 * i + 2]);
        const uint32_t u3 = hfma2(ga[2 * i + 1], hadd2(pk[4 * i + 3], v[i].w), xr[4 * i + 3]);
        xr[4 * i] = u0; xr[4 * i + 1] = u1; xr[4 * i + 2] = u2; xr[4 * i + 3] = u3;
        mma16816(ds, u0, u1, u2, u3, bw[i].x, bw[i].y);
        mma16816(dl, u0, u1, u2, u3, bw[i].z, bw[i].w);
        mma16816(q0, u0, u1, u2, u3, u0, u2);
        mma16816(q1, u0, u1, u2, u3, u1, u3);
      }
      const float sqa = (g & 1) ? q0[1] : q0[0], sqb = (g & 1) ? q1[3] : q1[2], dta = ds[1] + dl[1], dtb = ds[3] + dl[3];
      if (tq == (g >> 1)) {
        st_b128(sg + cj * 64, __float_as_uint(ds[0]), __float_as_uint(sqa), __float_as_uint(dta), tag);
        st_b128(sg + cj * 64 + 32, __float_as_uint(ds[2]), __float_as_uint(sqb), __float_as_uint(dtb), tag);
      }
#pragma unroll
      for (int k = 0; k < 4; k++) sv[k] = ld_b128(sp[k]);
      mbar_wait(bar_xres, 0);
      const float sqc = __shfl_sync(0xffffffffu, sqa, g * 4 + (g >> 1)), sqd = __shfl_sync(0xffffffffu, sqb, g * 4 + (g >> 1));
      own = (tq & 1) ? make_uint4(__float_as_uint(ds[2]), __float_as_uint(sqd), __float_as_uint(dtb), tag)
                     : make_uint4(__float_as_uint(ds[0]), __float_as_uint(sqc), __float_as_uint(dta), tag);
    }
    PROF(8, ct == PT, 29); STAMP(5);
    uint32_t mm, ih, il;
    float rbest;
    uint32_t wf[128];
    const uint32_t frow = (ln & 7) + (ln >> 4) * 8;
    const uint32_t wfo = base + (warp & 1) * 8192 + frow * 64 + ((((ln >> 3) & 1) ^ ((frow >> 1) & 3)) << 4);
#define LOAD_WF(m) _Pragma("unroll") for (int f = 0; f < 16; f++) {                                                   \
      const int r = ((f >> 1) * 4 + (m) * 2 + (f & 1)) * 4;                                                           \
      ldmatrix4t(((wfo + unit_of((m) ? FT_U : FT_G, warp >> 1)) ^ ((f & 1) * 32)) + (f >> 1) * 1024, wf[r], wf[r + 1], wf[r + 2], wf[r + 3]); \
    }
    bool early;
    {
#pragma unroll
      for (int i = 0; i < 16; i += 2) stmatrix4((trow ^ ((i & 7) << 4)) + (i >> 3) * 16384, xr[2 * i], xr[2 * i + 1], xr[2 * i + 2], xr[2 * i + 3]);
      const uint4 cst = lds4(par + PAR_CONST);
      const float A1 = __uint_as_float(cst.x), A2 = __uint_as_float(cst.z);
      uint32_t n = 0;
      early = false;
#pragma unroll 1
      while (true) {
        if (!early && (b >= NFFN || __all_sync(0xffffffffu, mbar_test(bar_box + (warp >> 1) * 8, 0)))) {
          early = true;
          LOAD_WF(0);
          __syncwarp();
          mbar_arrive_pred(bar_gate, lane0);
        }
        uint32_t miss;
        asm volatile("{ .reg .pred p0, p1, p2, p3; .reg .b64 u, v; .reg .b128 w;\n"
                     "setp.ge.u32 p0, %22, 2; setp.ne.and.u32 p0, %4, %21, p0; setp.ne.u32 p1, %8, %21; setp.ne.u32 p2, %12, %21; setp.ne.u32 p3, %16, %21;\n"
                     "@p0 ld.relaxed.gpu.global.v4.u32 {%1, %2, %3, %4}, [%17];\n"
                     "@p1 ld.relaxed.gpu.global.v4.u32 {%5, %6, %7, %8}, [%18];\n"
                     "@p2 ld.relaxed.gpu.global.v4.u32 {%9, %10, %11, %12}, [%19];\n"
                     "@p3 ld.relaxed.gpu.global.v4.u32 {%13, %14, %15, %16}, [%20];\n"
                     "or.pred p0, p0, p1; or.pred p2, p2, p3; or.pred p0, p0, p2; vote.sync.any.pred p0, p0, 0xffffffff; selp.u32 %0, 1, 0, p0; }"
                     : "=r"(miss), "+r"(sv[0].x), "+r"(sv[0].y), "+r"(sv[0].z), "+r"(sv[0].w), "+r"(sv[1].x), "+r"(sv[1].y), "+r"(sv[1].z), "+r"(sv[1].w),
                       "+r"(sv[2].x), "+r"(sv[2].y), "+r"(sv[2].z), "+r"(sv[2].w), "+r"(sv[3].x), "+r"(sv[3].y), "+r"(sv[3].z), "+r"(sv[3].w)
                     : "l"(sp[0]), "l"(sp[1]), "l"(sp[2]), "l"(sp[3]), "r"(tag), "r"(tq) : "memory");
        if (!miss) break;
        watchdog(n);
      }
      const uint4 v0 = tq < 2 ? own : sv[0], v1 = sv[1], v2 = sv[2], v3 = sv[3];
      PROF(8, ct == PT, 30); STAMP(6);
      float su = (__uint_as_float(v0.x) + __uint_as_float(v1.x)) + (__uint_as_float(v2.x) + __uint_as_float(v3.x));
      float sq = (__uint_as_float(v0.y) + __uint_as_float(v1.y)) + (__uint_as_float(v2.y) + __uint_as_float(v3.y));
      float dt = (__uint_as_float(v0.z) + __uint_as_float(v1.z)) + (__uint_as_float(v2.z) + __uint_as_float(v3.z));
      su += __shfl_xor_sync(0xffffffffu, su, 2); sq += __shfl_xor_sync(0xffffffffu, sq, 2); dt += __shfl_xor_sync(0xffffffffu, dt, 2);
      const float m = su * (1.f / DM);
      float mb, sd;
      ln_scalars(m, fmaxf(sq * (1.f / DM) - m * m, 0.f), mb, sd);
      const float inv = rcp(sd);
      rbest = (dt - mb * A1) * inv + A2;
      mm = pack_bf(mb, mb);
      ih = pack_bf(inv, inv);
      const float lo = inv - bf_lo(ih);
      il = pack_bf(lo, lo);
    }
    int ibest;
    {
      const uint32_t bits = __float_as_uint(rbest);
      const uint32_t key = (((int)bits < 0 ? ~bits : bits | 0x80000000u) & ~0x1ffu) | ((127 - lrow0 - (tq & 1) * 8) << 2) | tag;
      sts1(par + PAR_RED + warp * 4, __reduce_max_sync(0xffffffffu, key));
      PROF(8, ct == PT, 38); STAMP(7);
      bar_sync(1, 256);
      const uint4 ka = lds4(par + PAR_RED), kb = lds4(par + PAR_RED + 16);
      const uint32_t k2 = max(max(max(ka.x, ka.y), max(ka.z, ka.w)), max(max(kb.x, kb.y), max(kb.z, kb.w)));
      if (ct < CR && cj == 0) st_relaxed(g_cand + ct * 512 + rb * CS, k2);
      ibest = 127 - ((k2 >> 2) & 127);
    }
    PROF(8, ct == PT, 39); STAMP(8);
    if ((ibest >> 4) == warp) {
      const int src = (ibest & 7) * 4 + ((ibest >> 3) & 1), ch = g * 2;
      const uint32_t cm = __shfl_sync(0xffffffffu, mm, src), ch_ = __shfl_sync(0xffffffffu, ih, src), cl = __shfl_sync(0xffffffffu, il, src);
      const uint32_t xa = res + (ch >> 3) * 16384 + ibest * 128 + (((ch & 7) ^ (ibest & 7)) << 4) + tq * 4;
      const uint32_t x0 = lds1(xa), x1 = lds1(xa ^ 16);
      const uint2 p0 = lds2(par + PAR_T2 + ch * 64 + tq * 16), p1 = lds2(par + PAR_T2 + ch * 64 + 64 + tq * 16);
      uint32_t* dst = g_row + rb * 2 * DM + cj * 128 + ln * 4;
      st_pairs(dst, ln_mod(x0, cm, ch_, cl, p0.x, p0.y), ln_mod(x1, cm, ch_, cl, p1.x, p1.y), tag);
      st_pairs(dst + DM, x0, x1, tag);
      __syncwarp();
    }
    PROF(8, ct == PT, 37); STAMP(9);
    uint32_t wd[64];
    const uint32_t wda = base + unit_of(FT_D, warp >> 1) + (warp & 1) * 8192 + frow * 128 + ((((ln >> 3) & 1) ^ (ln & 7)) << 4);
#define LOAD_WD(f) ldmatrix4t((wda ^ ((((f) >> 1) & 3) * 32)) + ((f) >> 3) * 4096 + ((f) & 1) * 2048, wd[4 * (f)], wd[4 * (f) + 1], wd[4 * (f) + 2], wd[4 * (f) + 3])
    if (!early) {
      if (b < NFFN) mbar_wait(bar_box + (warp >> 1) * 8, 0);
      LOAD_WF(0);
      __syncwarp();
      mbar_arrive_pred(bar_gate, lane0);
    }
    if (b < NFFN) {
      const uint32_t own = base + unit_of(FT_G, warp >> 1) + (warp & 1) * 8192;
      mbar_wait(bar_box + (4 + (warp >> 1)) * 8, 0);
      LOAD_WF(1);
      uint32_t* const ydst = ypart_slot(b, warp * 16 + (tq & 1) * 8 + g);
      PROF(8, ct == PT, 31); STAMP(10);
      bool wdok;
      {
        uint32_t n = 0;
        while (!(wdok = __all_sync(0xffffffffu, mbar_test(bar_box + (8 + (warp >> 1)) * 8, 0))) && !__all_sync(0xffffffffu, mbar_test(bar_sel, 0))) watchdog(n);
      }
      if (wdok) {
#pragma unroll
        for (int f = 0; f < 16; f++) LOAD_WD(f);
      }
      STAMP(11);
      mbar_wait(bar_sel, 0);
      PROF(8, ct == PT, 33); STAMP(12);
      float d[8][4];
#pragma unroll
      for (int i = 0; i < 4; i++) { d[i][0] = 0.f; d[i][1] = 0.f; d[i][2] = 0.f; d[i][3] = 0.f; }
#pragma unroll
      for (int ks = 0; ks < 8; ks++) {
        const uint2 hb = lds2(own + 256 + ks * 32 + tq * 8);
#pragma unroll
        for (int mt = 0; mt < 4; mt++) {
          const int r = ks * 16 + mt * 4;
          mma16816(d[mt], wf[r], wf[r + 1], wf[r + 2], wf[r + 3], hb.x, hb.y);
        }
      }
      sts2(own + (tq * 8 + g) * 8, __float_as_uint((tq & 2) ? ((tq & 1) ? d[1][2] : d[1][0]) : ((tq & 1) ? d[0][2] : d[0][0])),
           __float_as_uint((tq & 2) ? ((tq & 1) ? d[3][2] : d[3][0]) : ((tq & 1) ? d[2][2] : d[2][0])));
      bar_sync(1, 256);
      uint32_t ab[4];
      {
        float G = 0.f, U = 0.f;
        uint2 pv[8];
#pragma unroll
        for (int w8 = 0; w8 < 8; w8++) pv[w8] = lds2(base + ln * 8 + ((FT_G >> (w8 >> 1) * 4) & 15) * UNIT + (w8 & 1) * 8192);
#pragma unroll
        for (int w8 = 0; w8 < 8; w8 += 2) {
          G += __uint_as_float(pv[w8].x) + __uint_as_float(pv[w8 + 1].x);
          U += __uint_as_float(pv[w8].y) + __uint_as_float(pv[w8 + 1].y);
        }
        const float act = rbf(silu_f(rbf(G))) * rbf(U);
        const uint32_t pk = pack_bf(act, __shfl_down_sync(0xffffffffu, act, 1));
#pragma unroll
        for (int i = 0; i < 4; i++) ab[i] = __shfl_sync(0xffffffffu, pk, i * 8 + tq * 2);
      }
      if (!wdok) {
        mbar_wait(bar_box + (8 + (warp >> 1)) * 8, 0);
#pragma unroll
        for (int f = 0; f < 16; f++) LOAD_WD(f);
      }
      PROF(8, ct == PT, 34); STAMP(13);
#pragma unroll
      for (int mt = 0; mt < 8; mt++) {
        d[mt][0] = 0.f; d[mt][1] = 0.f; d[mt][2] = 0.f; d[mt][3] = 0.f;
        mma16816(d[mt], wd[mt * 8], wd[mt * 8 + 1], wd[mt * 8 + 2], wd[mt * 8 + 3], ab[0], ab[1]);
        mma16816(d[mt], wd[mt * 8 + 4], wd[mt * 8 + 5], wd[mt * 8 + 6], wd[mt * 8 + 7], ab[2], ab[3]);
      }
      uint32_t yw[4];
#pragma unroll
      for (int i = 0; i < 4; i++) yw[i] = (tq & 1) ? pack_bf(d[2 * i][2], d[2 * i + 1][2]) : pack_bf(d[2 * i][0], d[2 * i + 1][0]);
      if (tq < 2) st_b128(ydst, (yw[0] & ~1u) | (tag & 1), (yw[1] & ~1u) | (tag >> 1), yw[2], yw[3]);
      PROF(8, ct == PT, 35); STAMP(14);
    }
    mbar_wait(bar_sel, 0);
    mbar_arrive_pred(bar_win, ct == 0);
    const int iwin = lds1(par + PAR_CONST + 60) & 0x7ff;
    const bool cand = (iwin >> 4) == rb * 8 + warp;
    {
      const uint32_t mm0 = __shfl_sync(0xffffffffu, mm, ln & ~1), mm1 = __shfl_sync(0xffffffffu, mm, ln | 1);
      const uint32_t ih0 = __shfl_sync(0xffffffffu, ih, ln & ~1), ih1 = __shfl_sync(0xffffffffu, ih, ln | 1);
      const uint32_t il0 = __shfl_sync(0xffffffffu, il, ln & ~1), il1 = __shfl_sync(0xffffffffu, il, ln | 1);
#pragma unroll 1
      for (int hf = 0; hf < 2; hf++) {
        uint32_t x[16];
#pragma unroll
        for (int i = 0; i < 8; i += 2) ldmatrix4((trow ^ (i << 4)) + hf * 16384, x[2 * i], x[2 * i + 1], x[2 * i + 2], x[2 * i + 3]);
#pragma unroll
        for (int i = 0; i < 8; i++) {
          const uint4 pv = lds4(par + PAR_T2 + (hf * 8 + i) * 64 + tq * 16);
          x[2 * i] = hfma2(hfma2(ln_norm(x[2 * i], mm0, ih0, il0), pv.x, pv.y), pv.z, x[2 * i]);
          x[2 * i + 1] = hfma2(hfma2(ln_norm(x[2 * i + 1], mm1, ih1, il1), pv.x, pv.y), pv.z, x[2 * i + 1]);
        }
#pragma unroll
        for (int i = 0; i < 8; i += 2) stmatrix4((trow ^ (i << 4)) + hf * 16384, x[2 * i], x[2 * i + 1], x[2 * i + 2], x[2 * i + 3]);
        if (!cand) fence_async_smem();
        __syncwarp();
        if (!cand && elect_one()) {
          tma2d_store(&maps.out, res + hf * 16384 + warp * 2048, cj * 128 + hf * 64, rb * 128 + warp * 16);
          asm volatile("cp.async.bulk.commit_group;" ::: "memory");
        }
      }
    }
    if (cand) {
      const int wrow0 = warp * 16;
#pragma unroll 2
      for (int p = 0; p < 8; p++) {
        const int row = 2 * p + (ln >> 4), ch = ln & 15;
        const uint4 v = lds4(res + (ch >> 3) * 16384 + (wrow0 + row) * 128 + (((ch & 7) ^ (row & 7)) << 4));
        if (rb * 128 + wrow0 + row != iwin) *reinterpret_cast<uint4*>(P.out + (size_t)(rb * 128 + wrow0 + row) * DM + cj * 128 + ch * 8) = v;
      }
    }
    asm volatile("cp.async.bulk.wait_group.read 0;" ::: "memory");
    PROF(8, ct == PT, 11); STAMP(15);
    cluster_wait();
  }
}

typedef CUresult (*EncodeFn)(CUtensorMap*, CUtensorMapDataType, cuuint32_t, void*, const cuuint64_t*, const cuuint64_t*,
                             const cuuint32_t*, const cuuint32_t*, CUtensorMapInterleave, CUtensorMapSwizzle,
                             CUtensorMapL2promotion, CUtensorMapFloatOOBfill);

void map2d(EncodeFn enc, CUtensorMap* m, const void* p, uint64_t rows, uint64_t cols, uint32_t brows) {
  cuuint64_t dims[2] = {cols, rows}, strides[1] = {cols * 2};
  cuuint32_t box[2] = {64, brows}, es[2] = {1, 1};
  enc(m, CU_TENSOR_MAP_DATA_TYPE_BFLOAT16, 2, const_cast<void*>(p), dims, strides, box, es, CU_TENSOR_MAP_INTERLEAVE_NONE,
      CU_TENSOR_MAP_SWIZZLE_128B, CU_TENSOR_MAP_L2_PROMOTION_L2_256B, CU_TENSOR_MAP_FLOAT_OOB_FILL_NONE);
}
void map2d_narrow(EncodeFn enc, CUtensorMap* m, const void* p, uint64_t rows, uint64_t cols, uint32_t brows) {
  cuuint64_t dims[2] = {cols, rows}, strides[1] = {cols * 2};
  cuuint32_t box[2] = {32, brows}, es[2] = {1, 1};
  enc(m, CU_TENSOR_MAP_DATA_TYPE_BFLOAT16, 2, const_cast<void*>(p), dims, strides, box, es, CU_TENSOR_MAP_INTERLEAVE_NONE,
      CU_TENSOR_MAP_SWIZZLE_64B, CU_TENSOR_MAP_L2_PROMOTION_L2_64B, CU_TENSOR_MAP_FLOAT_OOB_FILL_NONE);
}
void map3d(EncodeFn enc, CUtensorMap* m, const void* p, uint64_t rows, uint64_t cols, uint32_t brows, uint32_t nch) {
  cuuint64_t dims[3] = {64, rows, cols / 64}, strides[2] = {cols * 2, 128};
  cuuint32_t box[3] = {64, brows, nch}, es[3] = {1, 1, 1};
  enc(m, CU_TENSOR_MAP_DATA_TYPE_BFLOAT16, 3, const_cast<void*>(p), dims, strides, box, es, CU_TENSOR_MAP_INTERLEAVE_NONE,
      CU_TENSOR_MAP_SWIZZLE_128B, CU_TENSOR_MAP_L2_PROMOTION_L2_256B, CU_TENSOR_MAP_FLOAT_OOB_FILL_NONE);
}

}

extern "C" void kernel_launch(void* const* d_in, const int* in_sizes, int n_in, void* d_out, int out_size) {
  (void)in_sizes; (void)n_in; (void)out_size;
  static EncodeFn enc = nullptr;
  if (!enc) {
    void* fn = nullptr;
    cudaDriverEntryPointQueryResult st;
    cudaGetDriverEntryPoint("cuTensorMapEncodeTiled", &fn, cudaEnableDefault, &st);
    enc = (EncodeFn)fn;
    cudaFuncSetAttribute(fused_kernel, cudaFuncAttributeMaxDynamicSharedMemorySize, SMEM_BYTES);
  }
  Maps maps;
  map2d(enc, &maps.x, d_in[0], SEQ, DM, 128);
  map2d(enc, &maps.out, d_out, SEQ, DM, 16);
  map3d(enc, &maps.wq, d_in[3], DM, NQ, 64, 2);
  map3d(enc, &maps.k, d_in[1], 4 * SK, 128, 128, 1);
  map3d(enc, &maps.v, d_in[2], 4 * SK, 128, 128, 1);
  map3d(enc, &maps.wo, d_in[4], NQ, DM, 64, 2);
  map2d_narrow(enc, &maps.wg, d_in[7], DM, FF, 256);
  map2d_narrow(enc, &maps.wu, d_in[8], DM, FF, 256);
  map3d(enc, &maps.wd, d_in[9], FF, DM, 32, 4);
  map2d_narrow(enc, &maps.wm, d_in[11], DM, NMOD, 256);
  Ptrs p;
  p.x = (const __nv_bfloat16*)d_in[0];
  p.w_r = (const __nv_bfloat16*)d_in[6];
  p.w_gate = (const __nv_bfloat16*)d_in[7];
  p.w_up = (const __nv_bfloat16*)d_in[8];
  p.w_down = (const __nv_bfloat16*)d_in[9];
  p.c = (const __nv_bfloat16*)d_in[10];
  p.w_mod = (const __nv_bfloat16*)d_in[11];
  p.out = (__nv_bfloat16*)d_out;
  fused_kernel<<<NMAIN + NHELP, 384, SMEM_BYTES>>>(maps, p);
}
```

```cpp
#include <cuda_runtime.h>
#include <cuda_bf16.h>
#include <cuda.h>
#include <stdint.h>
#include <type_traits>

#define HD 2
#define HDX 2
#define NRS 8
#define OSL 900
#define OSL2 400
#define RSL 40
#define BIAS 102.f
#define VREL 5
#define OPS 8192
#define ODS1 5
#define ODS 7
#define PG0 15
#define WB 2
#define WN 20
#define HU 32
#define RES0 17
#define RES1 20
#define GOST 20
#define NS1 5
#define LD2 4
#define FPACE0 2
#define FPACE 3
#define CR 8
#define CS 8

namespace {

constexpr int SEQ = 2048, DM = 1024, NQ = 4096, SK = 2048, WIN = 512, FF = 3584, NMOD = 6144;
constexpr int NMAIN = 128, NHELP = 4, NFFN = 112;
constexpr int NSLOT = 4, SLOT_BYTES = 32768, UNIT = 16384, GST_BYTES = 3 * UNIT;
constexpr uint32_t XT1 = 0xDCBA, XT2 = 0x9687;
constexpr uint32_t WT0 = 0xA741, WT1 = 0x7420, WT2 = 0x4A20;
constexpr uint32_t AT0 = WT1, AT1 = WT2;
constexpr uint32_t QT = 0xDC9696DC;
constexpr int OFF_STAGE = 12 * UNIT;
constexpr uint32_t FT_G = 0x07B3, FT_U = 0xA628, FT_D = 0x5149;
constexpr int OFF_RES = 12 * UNIT;
constexpr int OFF_PAR = 14 * UNIT;
constexpr int OFF_BAR = OFF_PAR + 2528;
constexpr int SMEM_BYTES = OFF_BAR + 544;
static_assert(SMEM_BYTES <= 232448, "smem");

constexpr int PAR_T1 = 0;
constexpr int PAR_T2 = 512;
constexpr int PAR_CONST = 1536;
constexpr int PAR_RED = 1600;
constexpr int PAR_SINK = 2176;

struct Maps {
  CUtensorMap x, wq, k, v, wo, wg, wu, wd, wm, out;
};
struct Ptrs {
  const __nv_bfloat16 *x, *w_r, *c, *w_mod, *w_gate, *w_up, *w_down;
  __nv_bfloat16* out;
};

__device__ __align__(1024) uint8_t g_act[16 * 80 * UNIT];
__device__ __align__(128) uint32_t g_mod[NMOD];
__device__ __align__(128) uint32_t g_modp[2 * 2 * DM];
__device__ __align__(128) uint32_t g_ln1[SEQ * 4];
__device__ __align__(128) uint32_t g_cnt_h[16 * 32];
__device__ __align__(128) uint32_t g_cnt_o[128 * 32];
__device__ __align__(128) uint32_t g_xch[NMAIN * 8 * 256 * 4];
__device__ __align__(128) uint32_t g_stats[8 * SEQ * 4];
__device__ __align__(128) uint32_t g_cand[CR * 512];
__device__ __align__(128) uint32_t g_row[16 * 2 * DM];
__device__ __align__(128) uint32_t g_ypart[NMAIN * NFFN * 4];
__device__ __forceinline__ uint32_t* ypart_slot(int writer, int reader) { return g_ypart + (writer * NMAIN + reader) * 4; }
__device__ uint32_t g_epoch;

__device__ __forceinline__ uint32_t fresh_lane() { uint32_t l; asm volatile("mov.u32 %0, %%laneid;" : "=r"(l)); return l; }
__device__ __forceinline__ uint32_t frag_offset(int warp) {
  const uint32_t l = fresh_lane();
  return ((warp & 3) * 16 + (l & 15)) * 128 + (((l >> 4) ^ (l & 7)) << 4);
}
__device__ __forceinline__ bool elect_one() {
  uint32_t p;
  asm volatile("{ .reg .pred q; elect.sync _|q, 0xffffffff; selp.u32 %0, 1, 0, q; }" : "=r"(p));
  return p;
}
__device__ __forceinline__ uint32_t smem_u32(const void* p) { return (uint32_t)__cvta_generic_to_shared(p); }
__device__ __forceinline__ void mbar_init(uint32_t bar, uint32_t cnt) {
  asm volatile("mbarrier.init.shared::cta.b64 [%0], %1;" ::"r"(bar), "r"(cnt) : "memory");
}
__device__ __forceinline__ void mbar_expect_tx(uint32_t bar, uint32_t bytes) {
  asm volatile("mbarrier.arrive.expect_tx.shared::cta.b64 _, [%0], %1;" ::"r"(bar), "r"(bytes) : "memory");
}
__device__ __forceinline__ void mbar_arrive(uint32_t bar) {
  asm volatile("mbarrier.arrive.shared::cta.b64 _, [%0];" ::"r"(bar) : "memory");
}
__device__ __forceinline__ void mbar_arrive_pred(uint32_t bar, bool p) {
  asm volatile("{ .reg .pred p; setp.ne.b32 p, %1, 0; @p mbarrier.arrive.shared::cta.b64 _, [%0]; }" ::"r"(bar), "r"((int)p) : "memory");
}
__device__ __forceinline__ void mbar_arrive_cl(uint32_t bar, uint32_t off, bool p = true) {
  asm volatile("{ .reg .pred p, q; .reg .b32 a; setp.ne.b32 q, %2, 0; setp.ne.and.b32 p, %0, 0, q; add.u32 a, %0, %1; @p mbarrier.arrive.shared::cluster.b64 _, [a]; }"
               ::"r"(bar), "r"(off), "r"((int)p) : "memory");
}
__device__ __forceinline__ uint32_t mapa(uint32_t addr, uint32_t cta) {
  uint32_t r; asm("mapa.shared::cluster.u32 %0, %1, %2;" : "=r"(r) : "r"(addr), "r"(cta)); return r;
}
__device__ __forceinline__ void cluster_arrive() { asm volatile("barrier.cluster.arrive.relaxed.aligned;" ::: "memory"); }
__device__ __forceinline__ void cluster_wait() { asm volatile("barrier.cluster.wait.aligned;" ::: "memory"); }
__device__ __forceinline__ void watchdog(uint32_t& n) {
}
__device__ __forceinline__ void mbar_wait(uint32_t bar, uint32_t parity) {
  asm volatile("{\n.reg .pred p;\nWAIT_%=:\nmbarrier.try_wait.parity.shared::cta.b64 p, [%0], %1;\n@!p bra WAIT_%=;\n}" ::"r"(bar), "r"(parity) : "memory");
}
__device__ __forceinline__ bool mbar_test(uint32_t bar, uint32_t parity) {
  uint32_t ok;
  asm volatile("{\n.reg .pred p;\nmbarrier.test_wait.parity.shared::cta.b64 p, [%1], %2;\nselp.u32 %0, 1, 0, p;\n}" : "=r"(ok) : "r"(bar), "r"(parity) : "memory");
  return ok;
}
__device__ __forceinline__ uint64_t l2_stream() {
  uint64_t f; asm("createpolicy.fractional.L2::evict_first.b64 %0, 1.0;" : "=l"(f)); return f;
}
__device__ __forceinline__ uint64_t l2_normal() {
  uint64_t f; asm("createpolicy.fractional.L2::evict_normal.b64 %0, 1.0;" : "=l"(f)); return f;
}
__device__ __forceinline__ void tma2d(uint32_t dst, const CUtensorMap* m, int c0, int c1, uint32_t bar) {
  asm volatile("cp.async.bulk.tensor.2d.shared::cluster.global.mbarrier::complete_tx::bytes.L2::cache_hint [%0], [%1, {%3, %4}], [%2], %5;"
               ::"r"(dst), "l"(m), "r"(bar), "r"(c0), "r"(c1), "l"(l2_stream()) : "memory");
}
__device__ __forceinline__ void bulk_load(uint32_t dst, const void* src, uint32_t bytes, uint32_t bar) {
  asm volatile("cp.async.bulk.shared::cluster.global.mbarrier::complete_tx::bytes [%0], [%1], %2, [%3];" ::"r"(dst), "l"(src), "r"(bytes), "r"(bar) : "memory");
}
__device__ __forceinline__ void bulk_load_stream(uint32_t dst, const void* src, uint32_t bytes, uint32_t bar, uint64_t pol = l2_stream()) {
  asm volatile("cp.async.bulk.shared::cluster.global.mbarrier::complete_tx::bytes.L2::cache_hint [%0], [%1], %2, [%3], %4;"
               ::"r"(dst), "l"(src), "r"(bytes), "r"(bar), "l"(pol) : "memory");
}
__device__ __forceinline__ void tma2d_store(const CUtensorMap* m, uint32_t src, int c0, int c1) {
  asm volatile("cp.async.bulk.tensor.2d.global.shared::cta.bulk_group [%0, {%2, %3}], [%1];" ::"l"(m), "r"(src), "r"(c0), "r"(c1) : "memory");
}
__device__ __forceinline__ void bulk_store(void* dst, uint32_t src, uint32_t bytes) {
  asm volatile("cp.async.bulk.global.shared::cta.bulk_group [%0], [%1], %2;" ::"l"(dst), "r"(src), "r"(bytes) : "memory");
}
__device__ __forceinline__ int slice_of(int i) { return (i & 8) + ((0x76531420u >> (i & 7) * 4) & 7); }
__device__ __forceinline__ uint32_t unit_of(uint32_t table, uint32_t i) { return ((table >> (i * 4)) & 15) * UNIT; }
__device__ __forceinline__ void tma3d(uint32_t dst, const CUtensorMap* m, int c0, int c1, int c2, uint32_t bar) {
  asm volatile("cp.async.bulk.tensor.3d.shared::cluster.global.mbarrier::complete_tx::bytes.L2::cache_hint [%0], [%1, {%3, %4, %5}], [%2], %6;"
               ::"r"(dst), "l"(m), "r"(bar), "r"(c0), "r"(c1), "r"(c2), "l"(l2_stream()) : "memory");
}
template <bool STREAM>
__device__ __forceinline__ void tma3d_mc(uint32_t dst, const CUtensorMap* m, int c0, int c1, int c2, uint32_t bar) {
  if (STREAM)
    asm volatile("cp.async.bulk.tensor.3d.shared::cluster.global.mbarrier::complete_tx::bytes.multicast::cluster.L2::cache_hint [%0], [%1, {%3, %4, %5}], [%2], %6, %7;"
                 ::"r"(dst), "l"(m), "r"(bar), "r"(c0), "r"(c1), "r"(c2), "h"((uint16_t)3), "l"(l2_stream()) : "memory");
  else
    asm volatile("cp.async.bulk.tensor.3d.shared::cluster.global.mbarrier::complete_tx::bytes.multicast::cluster [%0], [%1, {%3, %4, %5}], [%2], %6;"
                 ::"r"(dst), "l"(m), "r"(bar), "r"(c0), "r"(c1), "r"(c2), "h"((uint16_t)3) : "memory");
}
__device__ __forceinline__ void prefetch_map(const CUtensorMap* m) {
  asm volatile("prefetch.tensormap [%0];" ::"l"(m) : "memory");
}
__device__ __forceinline__ void fence_async() { asm volatile("fence.proxy.async.global;" ::: "memory"); }
__device__ __forceinline__ void fence_async_smem() { asm volatile("fence.proxy.async.shared::cta;" ::: "memory"); }
__device__ __forceinline__ void bar_sync(int id, int n) { asm volatile("bar.sync %0, %1;" ::"r"(id), "r"(n) : "memory"); }
__device__ __forceinline__ void bar_arrive(int id, int n) { asm volatile("bar.arrive %0, %1;" ::"r"(id), "r"(n) : "memory"); }
__device__ __forceinline__ void wg_fence() { asm volatile("wgmma.fence.sync.aligned;" ::: "memory"); }
__device__ __forceinline__ void wg_commit() { asm volatile("wgmma.commit_group.sync.aligned;" ::: "memory"); }
template <int N> __device__ __forceinline__ void wg_wait() { asm volatile("wgmma.wait_group.sync.aligned %0;" ::"n"(N) : "memory"); }
__device__ __forceinline__ uint64_t make_desc(uint32_t addr, uint32_t lbo, uint32_t sbo) {
  return (uint64_t)((addr & 0x3FFFF) >> 4) | ((uint64_t)(lbo >> 4) << 16) | ((uint64_t)(sbo >> 4) << 32) | (1ull << 62);
}
__device__ __forceinline__ uint32_t ld_relaxed(const uint32_t* p) {
  uint32_t v; asm volatile("ld.relaxed.gpu.global.u32 %0, [%1];" : "=r"(v) : "l"(p) : "memory"); return v;
}
__device__ __forceinline__ uint32_t ld_acquire(const uint32_t* p) {
  uint32_t v; asm volatile("ld.acquire.gpu.global.u32 %0, [%1];" : "=r"(v) : "l"(p) : "memory"); return v;
}
__device__ __forceinline__ uint4 ld_relaxed4(const uint32_t* p) {
  uint4 v; asm volatile("ld.relaxed.gpu.global.v4.u32 {%0,%1,%2,%3}, [%4];" : "=r"(v.x), "=r"(v.y), "=r"(v.z), "=r"(v.w) : "l"(p) : "memory"); return v;
}
__device__ __forceinline__ void st_relaxed(uint32_t* p, uint32_t v) {
  asm volatile("st.relaxed.gpu.global.u32 [%0], %1;" ::"l"(p), "r"(v) : "memory");
}
__device__ __forceinline__ void st_relaxed4(uint32_t* p, uint32_t a, uint32_t b, uint32_t c, uint32_t d) {
  asm volatile("st.relaxed.gpu.global.v4.u32 [%0], {%1,%2,%3,%4};" ::"l"(p), "r"(a), "r"(b), "r"(c), "r"(d) : "memory");
}
__device__ __forceinline__ void st_b128(uint32_t* p, uint32_t a, uint32_t b, uint32_t c, uint32_t d) {
  asm volatile("{ .reg .b64 u, v; .reg .b128 w; mov.b64 u, {%1, %2}; mov.b64 v, {%3, %4}; mov.b128 w, {u, v}; st.relaxed.gpu.global.b128 [%0], w; }"
               ::"l"(p), "r"(a), "r"(b), "r"(c), "r"(d) : "memory");
}
__device__ __forceinline__ uint4 ld_b128(const uint32_t* p) {
  uint4 r;
  asm volatile("{ .reg .b64 u, v; .reg .b128 w; ld.relaxed.gpu.global.b128 w, [%4]; mov.b128 {u, v}, w; mov.b64 {%0, %1}, u; mov.b64 {%2, %3}, v; }"
               : "=r"(r.x), "=r"(r.y), "=r"(r.z), "=r"(r.w) : "l"(p) : "memory");
  return r;
}
__device__ __forceinline__ void st_pairs(uint32_t* p, uint32_t a, uint32_t b, uint32_t tag) {
  asm volatile("{ .reg .b64 u, v; mov.b64 u, {%1, %3}; mov.b64 v, {%2, %3}; st.relaxed.gpu.global.v2.b64 [%0], {u, v}; }"
               ::"l"(p), "r"(a), "r"(b), "r"(tag) : "memory");
}
__device__ __forceinline__ uint4 ld_pairs(const uint32_t* p) {
  uint4 v;
  asm volatile("{ .reg .b64 u, v; ld.relaxed.gpu.global.v2.b64 {u, v}, [%4]; mov.b64 {%0, %1}, u; mov.b64 {%2, %3}, v; }"
               : "=r"(v.x), "=r"(v.y), "=r"(v.z), "=r"(v.w) : "l"(p) : "memory");
  return v;
}
__device__ __forceinline__ uint2 ld_pair(const uint32_t* p) {
  uint2 v;
  asm volatile("{ .reg .b64 u; ld.relaxed.gpu.global.b64 u, [%2]; mov.b64 {%0, %1}, u; }" : "=r"(v.x), "=r"(v.y) : "l"(p) : "memory");
  return v;
}
__device__ __forceinline__ void red_release(uint32_t* p, uint32_t v) {
  asm volatile("red.release.gpu.global.add.u32 [%0], %1;" ::"l"(p), "r"(v) : "memory");
}
__device__ __forceinline__ uint32_t ldg_nc1(const void* p) {
  uint32_t v;
  asm volatile("ld.global.nc.u32 %0, [%1];" : "=r"(v) : "l"(p));
  return v;
}
__device__ __forceinline__ uint4 ldg_nc4(const void* p) {
  uint4 v; asm volatile("ld.global.nc.L1::no_allocate.v4.u32 {%0,%1,%2,%3}, [%4];" : "=r"(v.x), "=r"(v.y), "=r"(v.z), "=r"(v.w) : "l"(p)); return v;
}
__device__ __forceinline__ uint4 ldg_stream4(const void* p) {
  uint4 v;
  asm volatile("ld.global.nc.L1::no_allocate.L2::cache_hint.v4.u32 {%0,%1,%2,%3}, [%4], %5;" : "=r"(v.x), "=r"(v.y), "=r"(v.z), "=r"(v.w) : "l"(p), "l"(l2_stream()));
  return v;
}
__device__ __forceinline__ void stg4(void* p, uint4 v) {
  asm volatile("st.global.v4.u32 [%0], {%1,%2,%3,%4};" ::"l"(p), "r"(v.x), "r"(v.y), "r"(v.z), "r"(v.w) : "memory");
}
__device__ __forceinline__ void wait_counter(const uint32_t* p, uint32_t target) {
  uint32_t n = 0;
  while (__any_sync(0xffffffffu, (int)(ld_acquire(p) - target) < 0)) { watchdog(n); }
}
__device__ __forceinline__ uint32_t tagf(float v, uint32_t tag) { return (__float_as_uint(v) & ~3u) | tag; }
__device__ __forceinline__ bool tag_ok(uint4 v, uint32_t tag) { return (((v.x ^ tag) | (v.y ^ tag) | (v.z ^ tag) | (v.w ^ tag)) & 3u) == 0; }
__device__ __forceinline__ float untag_sum(uint32_t a, uint32_t b) { return __uint_as_float(a & ~3u) + __uint_as_float(b & ~3u); }
__device__ __forceinline__ uint4 poll4(const uint32_t* p, uint32_t tag) {
  uint4 v = ld_relaxed4(p);
  uint32_t n = 0;
  while (!__all_sync(0xffffffffu, tag_ok(v, tag))) { v = ld_relaxed4(p); watchdog(n); }
  return v;
}
__device__ __forceinline__ float bf_lo(uint32_t v) { return __uint_as_float(v << 16); }
__device__ __forceinline__ float bf_hi(uint32_t v) { return __uint_as_float(v & 0xffff0000u); }
__device__ __forceinline__ uint32_t pack_bf(float lo, float hi) {
  uint32_t r; asm("cvt.rn.bf16x2.f32 %0, %1, %2;" : "=r"(r) : "f"(hi), "f"(lo)); return r;
}
__device__ __forceinline__ float rbf(float v) { return __uint_as_float(pack_bf(0.f, v) & 0xffff0000u); }
__device__ __forceinline__ uint32_t hmul2(uint32_t a, uint32_t b) {
  uint32_t r; asm("mul.rn.bf16x2 %0, %1, %2;" : "=r"(r) : "r"(a), "r"(b)); return r;
}
__device__ __forceinline__ uint32_t hadd2(uint32_t a, uint32_t b) {
  uint32_t r; asm("add.rn.bf16x2 %0, %1, %2;" : "=r"(r) : "r"(a), "r"(b)); return r;
}
__device__ __forceinline__ uint32_t hsub2(uint32_t a, uint32_t b) {
  uint32_t r; asm("sub.rn.bf16x2 %0, %1, %2;" : "=r"(r) : "r"(a), "r"(b)); return r;
}
__device__ __forceinline__ float rcp(float x) { float r; asm("rcp.approx.ftz.f32 %0, %1;" : "=f"(r) : "f"(x)); return r; }
__device__ __forceinline__ float ex2(float x) { float r; asm("ex2.approx.ftz.f32 %0, %1;" : "=f"(r) : "f"(x)); return r; }
__device__ __forceinline__ void stmatrix4(uint32_t addr, uint32_t a, uint32_t b, uint32_t c, uint32_t d) {
  asm volatile("stmatrix.sync.aligned.m8n8.x4.shared.b16 [%0], {%1,%2,%3,%4};" ::"r"(addr), "r"(a), "r"(b), "r"(c), "r"(d) : "memory");
}
__device__ __forceinline__ void ldmatrix4(uint32_t addr, uint32_t& a, uint32_t& b, uint32_t& c, uint32_t& d) {
  asm volatile("ldmatrix.sync.aligned.m8n8.x4.shared.b16 {%0,%1,%2,%3}, [%4];" : "=r"(a), "=r"(b), "=r"(c), "=r"(d) : "r"(addr) : "memory");
}
__device__ __forceinline__ void ldmatrix4t(uint32_t addr, uint32_t& a, uint32_t& b, uint32_t& c, uint32_t& d) {
  asm volatile("ldmatrix.sync.aligned.m8n8.x4.trans.shared.b16 {%0,%1,%2,%3}, [%4];" : "=r"(a), "=r"(b), "=r"(c), "=r"(d) : "r"(addr) : "memory");
}
__device__ __forceinline__ void mma16816(float (&d)[4], uint32_t a0, uint32_t a1, uint32_t a2, uint32_t a3, uint32_t b0, uint32_t b1) {
  asm volatile("mma.sync.aligned.m16n8k16.row.col.f32.bf16.bf16.f32 {%0,%1,%2,%3}, {%4,%5,%6,%7}, {%8,%9}, {%0,%1,%2,%3};"
               : "+f"(d[0]), "+f"(d[1]), "+f"(d[2]), "+f"(d[3]) : "r"(a0), "r"(a1), "r"(a2), "r"(a3), "r"(b0), "r"(b1));
}
__device__ __forceinline__ void sts1(uint32_t a, uint32_t v) { asm volatile("st.shared.u32 [%0], %1;" ::"r"(a), "r"(v) : "memory"); }
__device__ __forceinline__ uint4 lds4(uint32_t a) {
  uint4 v; asm volatile("ld.shared.v4.u32 {%0,%1,%2,%3}, [%4];" : "=r"(v.x), "=r"(v.y), "=r"(v.z), "=r"(v.w) : "r"(a) : "memory"); return v;
}
__device__ __forceinline__ uint2 lds2(uint32_t a) {
  uint2 v; asm volatile("ld.shared.v2.u32 {%0,%1}, [%2];" : "=r"(v.x), "=r"(v.y) : "r"(a) : "memory"); return v;
}
__device__ __forceinline__ uint32_t lds1(uint32_t a) {
  uint32_t v; asm volatile("ld.shared.u32 %0, [%1];" : "=r"(v) : "r"(a) : "memory"); return v;
}
__device__ __forceinline__ void sts2(uint32_t a, uint32_t x, uint32_t y) { asm volatile("st.shared.v2.u32 [%0], {%1,%2};" ::"r"(a), "r"(x), "r"(y) : "memory"); }
__device__ __forceinline__ void sts4(uint32_t a, uint4 v) {
  asm volatile("st.shared.v4.u32 [%0], {%1,%2,%3,%4};" ::"r"(a), "r"(v.x), "r"(v.y), "r"(v.z), "r"(v.w) : "memory");
}
__device__ __forceinline__ float silu_f(float v) { return __fdividef(v, 1.f + __expf(-v)); }
__device__ __forceinline__ uint32_t hfma2(uint32_t a, uint32_t b, uint32_t c) {
  uint32_t r; asm("fma.rn.bf16x2 %0, %1, %2, %3;" : "=r"(r) : "r"(a), "r"(b), "r"(c)); return r;
}
__device__ __forceinline__ void split_inv(float sd, uint32_t& ih, uint32_t& il) {
  const float inv = rcp(sd);
  ih = pack_bf(inv, inv);
  const float lo = inv - bf_lo(ih);
  il = pack_bf(lo, lo);
}
__device__ __forceinline__ uint32_t ln_norm(uint32_t x, uint32_t mean2, uint32_t ih, uint32_t il) {
  const uint32_t d = hsub2(x, mean2);
  return hfma2(d, ih, hmul2(d, il));
}
__device__ __forceinline__ uint32_t ln_mod(uint32_t x, uint32_t mean2, uint32_t ih, uint32_t il, uint32_t c1, uint32_t sh) {
  return hadd2(hmul2(ln_norm(x, mean2, ih, il), c1), sh);
}

#define R8(a, i) "+f"(a[i]), "+f"(a[i + 1]), "+f"(a[i + 2]), "+f"(a[i + 3]), "+f"(a[i + 4]), "+f"(a[i + 5]), "+f"(a[i + 6]), "+f"(a[i + 7])
#define D64 "{%0,%1,%2,%3,%4,%5,%6,%7,%8,%9,%10,%11,%12,%13,%14,%15,%16,%17,%18,%19,%20,%21,%22,%23,%24,%25,%26,%27,%28,%29,%30,%31," \
            "%32,%33,%34,%35,%36,%37,%38,%39,%40,%41,%42,%43,%44,%45,%46,%47,%48,%49,%50,%51,%52,%53,%54,%55,%56,%57,%58,%59,%60,%61,%62,%63}"
template <int TB>
__device__ __forceinline__ void mma_ss(float (&d)[64], uint64_t da, uint64_t db, int sc) {
  asm volatile("{\n.reg .pred p;\nsetp.ne.b32 p, %66, 0;\n"
               "wgmma.mma_async.sync.aligned.m64n128k16.f32.bf16.bf16 " D64 ", %64, %65, p, 1, 1, 0, %67;\n}"
               : R8(d, 0), R8(d, 8), R8(d, 16), R8(d, 24), R8(d, 32), R8(d, 40), R8(d, 48), R8(d, 56)
               : "l"(da), "l"(db), "r"(sc), "n"(TB));
}
template <int TB>
__device__ __forceinline__ void mma_rs(float (&d)[64], uint32_t a0, uint32_t a1, uint32_t a2, uint32_t a3, uint64_t db, int sc) {
  asm volatile("{\n.reg .pred p;\nsetp.ne.b32 p, %69, 0;\n"
               "wgmma.mma_async.sync.aligned.m64n128k16.f32.bf16.bf16 " D64 ", {%64,%65,%66,%67}, %68, p, 1, 1, %70;\n}"
               : R8(d, 0), R8(d, 8), R8(d, 16), R8(d, 24), R8(d, 32), R8(d, 40), R8(d, 48), R8(d, 56)
               : "r"(a0), "r"(a1), "r"(a2), "r"(a3), "l"(db), "r"(sc), "n"(TB));
}
#define D128 "{%0,%1,%2,%3,%4,%5,%6,%7,%8,%9,%10,%11,%12,%13,%14,%15,%16,%17,%18,%19,%20,%21,%22,%23,%24,%25,%26,%27,%28,%29,%30,%31," \
             "%32,%33,%34,%35,%36,%37,%38,%39,%40,%41,%42,%43,%44,%45,%46,%47,%48,%49,%50,%51,%52,%53,%54,%55,%56,%57,%58,%59,%60,%61,%62,%63," \
             "%64,%65,%66,%67,%68,%69,%70,%71,%72,%73,%74,%75,%76,%77,%78,%79,%80,%81,%82,%83,%84,%85,%86,%87,%88,%89,%90,%91,%92,%93,%94,%95," \
             "%96,%97,%98,%99,%100,%101,%102,%103,%104,%105,%106,%107,%108,%109,%110,%111,%112,%113,%114,%115,%116,%117,%118,%119,%120,%121,%122,%123,%124,%125,%126,%127}"
#define R128(d, e) R8(d, 0), R8(d, 8), R8(d, 16), R8(d, 24), R8(d, 32), R8(d, 40), R8(d, 48), R8(d, 56), \
                   R8(e, 0), R8(e, 8), R8(e, 16), R8(e, 24), R8(e, 32), R8(e, 40), R8(e, 48), R8(e, 56)
__device__ __forceinline__ void mma256_ss(float (&d)[64], float (&e)[64], uint64_t da, uint64_t db, int sc) {
  asm volatile("{\n.reg .pred p;\nsetp.ne.b32 p, %130, 0;\n"
               "wgmma.mma_async.sync.aligned.m64n256k16.f32.bf16.bf16 " D128 ", %128, %129, p, 1, 1, 0, 1;\n}"
               : R128(d, e) : "l"(da), "l"(db), "r"(sc));
}
__device__ __forceinline__ void mma256_rs(float (&d)[64], float (&e)[64], uint32_t a0, uint32_t a1, uint32_t a2, uint32_t a3, uint64_t db) {
  asm volatile("{\n.reg .pred p;\nsetp.ne.b32 p, 1, 0;\n"
               "wgmma.mma_async.sync.aligned.m64n256k16.f32.bf16.bf16 " D128 ", {%128,%129,%130,%131}, %132, p, 1, 1, 1;\n}"
               : R128(d, e) : "r"(a0), "r"(a1), "r"(a2), "r"(a3), "l"(db));
}
template <int N> __device__ __forceinline__ void keep(float (&a)[N]) {
#pragma unroll
  for (int i = 0; i < N; i++) asm volatile("" : "+f"(a[i])::"memory");
}
template <int N> __device__ __forceinline__ void keep(uint32_t (&a)[N]) {
#pragma unroll
  for (int i = 0; i < N; i++) asm volatile("" : "+r"(a[i])::"memory");
}

#define STAMP(idx) do {} while (0)
#define PROF(grp, cond, idx) do {} while (0)

constexpr float SCL2 = 1.4426950408889634f * 0.08838834764831845f;

__device__ __forceinline__ void pack_p(const float (&s)[64], uint32_t (&p)[32]) {
#pragma unroll
  for (int i = 0; i < 32; i++) p[i] = pack_bf(s[2 * i], s[2 * i + 1]);
}

__device__ __forceinline__ void issue_qk(float (&s)[64], uint32_t q0, uint32_t q1, uint32_t kslot) {
  const uint64_t db = make_desc(kslot, 16, 1024), da0 = make_desc(q0, 16, 1024), da1 = make_desc(q1, 16, 1024);
#pragma unroll
  for (int kk = 0; kk < 8; kk++) mma_ss<0>(s, (kk < 4 ? da0 : da1) + (kk & 3) * 2, db + (kk >> 2) * 1024 + (kk & 3) * 2, kk != 0);
}
__device__ __forceinline__ void issue_pv(float (&o)[64], uint32_t (&p)[32], uint32_t vslot, int acc) {
  uint64_t db = make_desc(vslot, 16384, 1024);
#pragma unroll
  for (int kk = 0; kk < 8; kk++)
    mma_rs<1>(o, p[4 * kk], p[4 * kk + 1], p[4 * kk + 2], p[4 * kk + 3], db + kk * 128, kk == 0 ? acc : 1);
}

template <int H>
__device__ __forceinline__ void store_chunk(const float (&a)[64], uint32_t addr) {
#pragma unroll
  for (int i = 8 * H; i < 8 * H + 8; i += 2)
    stmatrix4(addr ^ ((i & 7) << 4), pack_bf(a[4 * i], a[4 * i + 1]), pack_bf(a[4 * i + 2], a[4 * i + 3]),
              pack_bf(a[4 * i + 4], a[4 * i + 5]), pack_bf(a[4 * i + 6], a[4 * i + 7]));
}
template <int H>
__device__ __forceinline__ void store_chunk(const float (&a)[64], float i0, float i1, uint32_t addr) {
#pragma unroll
  for (int i = 8 * H; i < 8 * H + 8; i += 2)
    stmatrix4(addr ^ ((i & 7) << 4), pack_bf(a[4 * i] * i0, a[4 * i + 1] * i0), pack_bf(a[4 * i + 2] * i1, a[4 * i + 3] * i1),
              pack_bf(a[4 * i + 4] * i0, a[4 * i + 5] * i0), pack_bf(a[4 * i + 6] * i1, a[4 * i + 7] * i1));
}
__device__ __forceinline__ float inv_quad_sum(float l) {
  l += __shfl_xor_sync(0xffffffffu, l, 1);
  l += __shfl_xor_sync(0xffffffffu, l, 2);
  return rcp(l);
}

__device__ __forceinline__ void write_table(uint32_t table, bool ca, uint32_t t, const uint4& m0, const uint4& m1) {
  float c0 = untag_sum(m0.x, m1.x), c1 = untag_sum(m0.y, m1.y), c2 = untag_sum(m0.z, m1.z), c3 = untag_sum(m0.w, m1.w);
  if (ca) { c0 = 1.f + rbf(c0); c1 = 1.f + rbf(c1); c2 = 1.f + rbf(c2); c3 = 1.f + rbf(c3); }
  const uint32_t d = table + (t >> 2) * 64 + (t & 1) * 32 + (t & 2) * 2 + (ca ? 0 : 8);
  sts1(d, pack_bf(c0, c1));
  sts1(d + 16, pack_bf(c2, c3));
}

__device__ __forceinline__ void ln_scalars(float mean, float var, float& mb, float& sd) {
  mb = rbf(mean);
  float r; asm("sqrt.approx.ftz.f32 %0, %1;" : "=f"(r) : "f"(rbf(rbf(var) + 1e-5f)));
  sd = rbf(r);
}

__global__ void __cluster_dims__(2, 1, 1) __launch_bounds__(384, 1) fused_kernel(const __grid_constant__ Maps maps, const Ptrs P) {
  extern __shared__ __align__(1024) uint8_t smem_raw[];
  const uint32_t base = smem_u32(smem_raw);
  const int tid = threadIdx.x, lane = tid & 31;
  const int warp = __shfl_sync(0xffffffffu, tid >> 5, 0);
  int b = blockIdx.x;
  if (b < NMAIN) {
    const int p = b >> 1;
    const int grp = p < 4 ? 7 : (p < 36 ? (p + 2) & 7 : (p - 30) % 7), k = p < 4 ? 4 + p : (p < 36 ? (p - 4) >> 3 : 4 + (p - 36) / 7);
    b = grp << 4 | k << 1 | (b & 1);
  }
  PROF(31, tid == 0, 0);

  if (b >= NMAIN) {
    float* sc = reinterpret_cast<float*>(smem_raw);
    float* red = sc + DM;
    for (int k = tid; k < DM; k += 384) sc[k] = rbf(silu_f(__bfloat162float(P.c[k])));
    __syncthreads();
    if (tid < 256) {
      const int col = 2048 + (b - NMAIN) * 1024 + (tid & 127) * 8, r0 = (tid >> 7) * 512;
      float acc[8];
#pragma unroll
      for (int e = 0; e < 8; e++) acc[e] = 0.f;
#pragma unroll 1
      for (int r = r0; r < r0 + 512; r += HU) {
        uint4 w[HU];
#pragma unroll
        for (int u = 0; u < HU; u++) w[u] = ldg_stream4(P.w_mod + (size_t)(r + u) * NMOD + col);
#pragma unroll
        for (int u = 0; u < HU; u++) {
          float s = sc[r + u];
          acc[0] += s * bf_lo(w[u].x); acc[1] += s * bf_hi(w[u].x); acc[2] += s * bf_lo(w[u].y); acc[3] += s * bf_hi(w[u].y);
          acc[4] += s * bf_lo(w[u].z); acc[5] += s * bf_hi(w[u].z); acc[6] += s * bf_lo(w[u].w); acc[7] += s * bf_hi(w[u].w);
        }
      }
      if (tid >= 128) {
#pragma unroll
        for (int e = 0; e < 8; e++) red[(tid & 127) * 8 + e] = acc[e];
      }
      const uint32_t tag = ld_relaxed(&g_epoch) % 3 + 1;
      bar_sync(1, 256);
      if (tid < 128) {
        uint32_t o[8];
#pragma unroll
        for (int e = 0; e < 8; e++) o[e] = __float_as_uint(rbf(acc[e] + red[tid * 8 + e])) | tag;
        st_relaxed4(g_mod + col, o[0], o[1], o[2], o[3]);
        st_relaxed4(g_mod + col + 4, o[4], o[5], o[6], o[7]);
        const uint4 wr = ldg_nc4(P.w_r + tid * 8);
        const uint32_t wv[4] = {wr.x, wr.y, wr.z, wr.w};
        float dsum = 0.f;
#pragma unroll
        for (int e = 0; e < 8; e++) {
          const float m = bf_hi(o[e]);
          dsum += (b == NMAIN + 2 ? rbf(1.f + m) : m) * ((e & 1) ? bf_hi(wv[e >> 1]) : bf_lo(wv[e >> 1]));
        }
#pragma unroll
        for (int k = 16; k > 0; k >>= 1) dsum += __shfl_xor_sync(0xffffffffu, dsum, k);
        if (lane == 0) st_relaxed(g_mod + (b - NMAIN) * 4 + warp, tagf(dsum, tag));
      }
    }
    PROF(2, tid == 0, 1);
    return;
  }

  const int rank = b & 1;
  const int rb = ((b >> 4) << 1) | rank, cj = (b >> 1) & 7;
  const bool late = b & 4;
  const uint32_t bfull = base + OFF_BAR, bempty = bfull + NSLOT * 8;
  const uint32_t gfull = bempty + NSLOT * 8, gempty = gfull + 32;
  const uint32_t bar_ofull = gempty + 32;
  const uint32_t bar_ofree = bar_ofull + 32;
  const uint32_t bar_par = bar_ofree + 32;
  const uint32_t bar_mod = bar_par + 8;
  const uint32_t bar_pread = bar_mod + 8;
  const uint32_t bar_xres = bar_pread + 8;
  const uint32_t bar_ring = bar_xres + 8;
  const uint32_t bar_box = bar_ring + 24;
  const uint32_t bar_go = bar_box + 96;
  const uint32_t bar_go2 = bar_go + 16;
  const uint32_t bar_cnt = bar_go + 24;
  const uint32_t xfull = bar_go + 40, xempty = xfull + 32;
  const uint32_t bar_hw = xempty + 32, bar_hx = bar_hw + 8;
  const uint32_t bar_hpub = bar_hx + 16;
  const uint32_t bar_win = bar_hpub + 16;
  const uint32_t bar_rx = bar_win + 8;
  const uint32_t bar_sel = bar_rx + 8;
  const uint32_t bar_gate = bar_sel + 8;
  const uint32_t bar_rel = bar_gate + 8;
  const uint32_t bar_od = bar_rel + 8;
  const uint32_t bar_mod2 = bar_od + 8;
  const uint32_t bar_res = bar_go + 8;
  const uint32_t stage = base + OFF_STAGE, par = base + OFF_PAR;

  if (warp == 10 && elect_one()) prefetch_map(&maps.wm);
  if (warp == 8 && elect_one()) {
    for (int s = 0; s < NSLOT; s++) { mbar_init(bfull + s * 8, 1); mbar_init(bempty + s * 8, 16); }
    for (int s = 0; s < 4; s++) { mbar_init(gfull + s * 8, 1); mbar_init(gempty + s * 8, 16); mbar_init(xfull + s * 8, 1); mbar_init(xempty + s * 8, 8); mbar_init(bar_ofree + s * 8, 1); mbar_init(bar_ofull + s * 8, 128); }
    mbar_init(bar_par, 64); mbar_init(bar_mod, 256); mbar_init(bar_pread, 2); mbar_init(bar_xres, 1);
    mbar_init(bar_ring, 8); mbar_init(bar_ring + 8, 8); mbar_init(bar_ring + 16, 8);
    mbar_init(bar_go, 1); mbar_init(bar_go2, 1); mbar_init(bar_cnt, 1); mbar_init(bar_cnt + 8, 1); mbar_init(bar_hpub, 8); mbar_init(bar_hpub + 8, 8); mbar_init(bar_res, 1); mbar_init(bar_win, 1); mbar_init(bar_rx, 1); mbar_init(bar_sel, 64); mbar_init(bar_gate, 8); mbar_init(bar_rel, 8); mbar_init(bar_od, 1); mbar_init(bar_mod2, 64);
    for (int s = 0; s < 12; s++) mbar_init(bar_box + s * 8, 1);
    asm volatile("fence.mbarrier_init.release.cluster;" ::: "memory");
    prefetch_map(&maps.x); prefetch_map(&maps.wq); prefetch_map(&maps.k); prefetch_map(&maps.v);
  }
  if (warp == 9 && elect_one()) {
    mbar_init(bar_hw, 1); mbar_init(bar_hx, 1); mbar_init(bar_hx + 8, 1);
    asm volatile("fence.mbarrier_init.release.cluster;" ::: "memory");
    mbar_expect_tx(bar_hw, 32768);
    mbar_expect_tx(bar_hx, 16384);
    mbar_expect_tx(bar_hx + 8, 16384);
    const __nv_bfloat16* xs = P.x + (size_t)(rb * 128 + cj * 16) * DM;
    bulk_load(base + 2 * GST_BYTES, xs, 16384, bar_hx);
    if (!late) {
      tma2d(stage, &maps.wm, (b >> 1) * 32, rank * 512, bar_hw);
      tma2d(stage + 16384, &maps.wm, (b >> 1) * 32, rank * 512 + 256, bar_hw);
    }
    bulk_load(base + 3 * GST_BYTES, xs + 8 * DM, 16384, bar_hx + 8);
  }
  cluster_arrive();

  if (warp >= 8) {
    asm volatile("setmaxnreg.dec.sync.aligned.u32 40;");
    if (warp < 10) bar_arrive(1, 320);
    const uint32_t epoch = ld_relaxed(&g_epoch);
    cluster_wait();
    if (warp == 8) {
      const int kvrow = (cj >> 1) * SK + (SK - WIN);
      int wch = cj * 8 + rank * 2;
#pragma unroll 1
      for (int ps = 0; ps < 3; ps++) {
        const CUtensorMap* mw = ps == 2 ? &maps.wo : &maps.wq;
        const uint32_t xt = ps == 1 ? XT1 : XT2, wt = ps == 0 ? WT0 : (ps == 1 ? WT1 : WT2);
        const int nst = ps == 2 ? 32 : 16;
#pragma unroll 1
        for (int i = 0; i < nst; i++) {
          const uint32_t bf = gfull + (i & 3) * 8;
          const int kt = ps == 2 ? (((cj & 1) * 4 + ((i >> 1) & 3)) * 4 + (i >> 3)) * 2 + (i & 1) : (ps ? i : slice_of(i) + (b & 14)) & 15;
          const uint32_t wd = base + unit_of(wt, i & 3) + rank * UNIT, xd = base + unit_of(xt, i & 3);
          const uint8_t* xs = g_act + (uint32_t)(rb * 80 + (ps - 1) * 16 + kt) * UNIT;
          if (ps == 0 && i == HD) mbar_wait(bar_mod, 0);
          if (ps == 2 && (i & 7) == 0 && i != 8) mbar_wait(i ? bar_cnt + i - 16 : bar_ofree + 24, 0);
          if ((i & 7) == 0) fence_async();
          if (i == RES0) mbar_wait(bar_res, 0);
          mbar_wait(bf, ((i >> 2) & 1) ^ 1);
          if (elect_one()) {
            mbar_expect_tx(bf, ps ? GST_BYTES : 2 * UNIT);
            if (ps && i < 2) bulk_load_stream(xd, xs, UNIT, bf);
            mbar_arrive_pred(bar_go, i == GOST);
            mbar_arrive_pred(bar_go2, ps == 1 && i == PG0);
            mbar_arrive_pred(bar_od, ps && i == (ps == 1 ? ODS1 : ODS) + 1);
            if (i == RES0) mbar_expect_tx(bar_xres, 32768);
          }
          const int wk = (i == 31 ? kt ^ (rank * 32) : kt) * 64, wc = i == 31 ? cj * 2 : wch;
          const uint64_t xp = i == 31 ? l2_normal() : l2_stream();
          mbar_wait(ps && i < 4 ? bempty + i * 8 : gempty + (i & 3) * 8, ((i >> 2) & 1) ^ 1);
          if (elect_one()) {
            tma3d_mc<true>(wd, mw, 0, wk, wc, bf);
            if (ps && i > 2) bulk_load_stream(xd, xs, UNIT, bf, xp);
            if (i == RES0 || i == RES1) tma2d(base + OFF_RES + (i == RES1) * UNIT, &maps.x, cj * 128 + (i == RES1) * 64, rb * 128, bar_xres);
          }
          if (ps && i == 2) {
            mbar_wait(bar_ofree + (ps - 1) * 16, 0);
            if (elect_one()) bulk_load_stream(xd, xs, UNIT, bf);
          }
        }
        if (ps == 2) break;
        wch = ps ? ((wch >> 3) ^ rank) * 2 : wch + 4;
#pragma unroll 1
        for (int u = 0; u < 16; u++) {
          const bool isk = (u == 0) || ((u & 1) && u < 15), kept = (0x1680 >> u) & 1;
          const int blk = (0x472FAD84u >> (u * 2)) & 3;
          const uint32_t sl = base + unit_of(ps ? AT1 : AT0, u & 3) + rank * UNIT, bf = bfull + (u & 3) * 8;
          mbar_wait(bf, ((u >> 2) & 1) ^ 1);
          if (!kept && elect_one()) mbar_expect_tx(bf, SLOT_BYTES);
          mbar_wait(u < 4 ? gempty + ((u + 1) >> 1) * 8 : bempty + (u & 3) * 8, ((u >> 2) & 1) ^ 1);
          if (elect_one()) {
            if (kept) mbar_arrive(bf);
            else if (ps && (blk >= 2 || u > 8)) tma3d_mc<true>(sl, isk ? &maps.k : &maps.v, 0, kvrow + blk * 128, rank, bf);
            else tma3d_mc<false>(sl, isk ? &maps.k : &maps.v, 0, kvrow + blk * 128, rank, bf);
          }
        }
      }
      if (elect_one()) mbar_expect_tx(bar_rx, UNIT);
      mbar_wait(bar_rel, 0);
      if (elect_one()) {
        bulk_load_stream(base + UNIT, g_act + (uint32_t)(rb * 80 + 16 + 63 - (cj & 1) * 32) * UNIT, UNIT, bar_rx);
      }
      if (b < NFFN) {
#pragma unroll 1
        for (int u = 0; u < 12; u++) {
          const uint32_t dst = base + unit_of(u < 4 ? FT_G : (u < 8 ? FT_U : FT_D), u & 3);
          if (elect_one()) mbar_expect_tx(bar_box + u * 8, UNIT);
          if (u == 0 || u == 2 || u == 8) mbar_wait(bar_ring + (u == 8 ? 16 : u * 4), 0);
          const int fp = u < 8 ? FPACE0 : FPACE;
          if (u >= fp) mbar_wait(bar_box + (u - fp) * 8, 0);
          if (elect_one()) {
            if (u < 8) tma2d(dst, u < 4 ? &maps.wg : &maps.wu, b * 32, (u & 3) * 256, bar_box + u * 8);
            else tma3d(dst, &maps.wd, 0, b * 32, (u - 8) * 4, bar_box + u * 8);
          }
        }
      }
    } else if (warp == 9) {
      const uint32_t target = 8 * (epoch + 1);
      uint32_t hmask = 0;
#pragma unroll 1
      for (int i = 0; i < 16; i++) {
        if (i == HDX) mbar_wait(bar_mod, 0);
        const int kt = (2 * cj + slice_of(i)) & 15;
        const uint32_t need = i == 15 ? 0xffffu : 1u << kt;
        if (i >= NRS && (hmask & need) != need) {
          uint32_t n = 0;
          do { hmask = __ballot_sync(0xffffffffu, ld_acquire(&g_cnt_h[rb * 32 + (lane & 15)]) == epoch + 1); watchdog(n); } while ((hmask & need) != need);
          PROF(1, lane == 0 && i == NRS, 26);
          fence_async();
        }
        mbar_wait(xempty + (i & 3) * 8, ((i >> 2) & 1) ^ 1);
        if (elect_one()) {
          mbar_expect_tx(xfull + (i & 3) * 8, UNIT);
          if (i < NRS) tma2d(base + (i & 3) * GST_BYTES, &maps.x, kt * 64, rb * 128, xfull + (i & 3) * 8);
          else bulk_load_stream(base + (i & 3) * GST_BYTES, g_act + (uint32_t)(rb * 80 + kt) * UNIT, UNIT, xfull + (i & 3) * 8);
        }
      }
      prefetch_map(&maps.wo);
#pragma unroll 1
      for (int t = 0; t < 4; t++) {
        if (t & 1) mbar_wait(bar_od, t >> 1);
        const int ops = OPS >> (t & 1);
#pragma unroll 1
        for (int p = 0; p < 32768; p += ops) {
          const uint32_t w = p >> 14, c = (p >> 13) & 1, off = w * 8192 + (p & 8191);
          mbar_wait(bar_ofull + (t & 1) * 16 + w * 8, t >> 1);
          if (elect_one()) {
            bulk_store(g_act + (uint32_t)(rb * 80 + 16 + (cj * 4 + t) * 2 + c) * UNIT + off, base + unit_of(QT, 2 * t + c) + off, ops);
            asm volatile("cp.async.bulk.commit_group;" ::: "memory");
            asm volatile("cp.async.bulk.wait_group.read 0;" ::: "memory");
          }
        }
        if (elect_one()) {
          mbar_arrive(t < 3 ? bar_ofree + t * 8 : bar_res);
          asm volatile("cp.async.bulk.wait_group 0;" ::: "memory");
          fence_async();
          red_release(&g_cnt_o[((rb * 4 + t) * 2 + (cj >> 2)) * 32], 2);
        }
        if (t) {
          wait_counter(&g_cnt_o[(rb * 8 + 2 * t + (cj & 1)) * 32], target);
          if (t & 1) wait_counter(&g_cnt_o[(rb * 8 + (t == 1 ? cj & 1 : 7 - (cj & 1))) * 32], target);
          if (elect_one()) mbar_arrive(t == 1 ? bar_ofree + 24 : bar_cnt + t * 8 - 16);
        }
      }
      PROF(2, lane == 0, 27);
      const uint32_t tag = epoch % 3 + 1;
      const uint32_t* inbox = g_cand + (b >> 4) % CR * 512 + (lane & 15) * CS;
      mbar_wait(bar_ring + 16, 0);
      uint32_t c0 = ld_relaxed(inbox), n = 0;
#define CAND_STEP(cv)                                                                                        \
      {                                                                                                      \
        const bool valid = (cv & 3u) == tag, all = __all_sync(0xffffffffu, valid);                           \
        const uint32_t best = __reduce_max_sync(0xffffffffu, valid ? cv : 0u);                               \
        const uint32_t blk = __ffs(__ballot_sync(0xffffffffu, cv == best)) - 1;                              \
        if (best) sts2(par + PAR_CONST + 56, best, (blk << 7 | (~best >> 2 & 127)) | (all ? 0x1800 : 0x800)); \
        if (all) break;                                                                                      \
        cv = ld_relaxed(inbox);                                                                              \
      }
      while (true) { CAND_STEP(c0) watchdog(n); }
    } else {
      const int t2 = tid - 320;
      if (late && warp == 10) {
        mbar_wait(bar_hx, 0);
        if (elect_one()) {
          tma2d(stage, &maps.wm, (b >> 1) * 32, rank * 512, bar_hw);
          tma2d(stage + 16384, &maps.wm, (b >> 1) * 32, rank * 512 + 256, bar_hw);
        }
      }
      {
        const uint32_t tag = epoch % 3 + 1;
        mbar_wait(bar_hx + 8, 0);
        mbar_wait(bar_hw, 0);
        __nanosleep(late ? OSL2 : OSL);
        {
          const uint32_t t7 = (warp & 1) * 64 + (lane >> 4) * 32 + 16 + (lane & 15);
          const uint32_t* pm = g_modp + ((cj * 128 + t7 * 4) & (DM - 1));
          uint4 m0, m1, m2, m3;
          uint32_t n = 0;
          do {
            m0 = ld_relaxed4(pm); m1 = ld_relaxed4(pm + 2 * DM); m2 = ld_relaxed4(pm + DM); m3 = ld_relaxed4(pm + 3 * DM);
            watchdog(n);
          } while (!__all_sync(0xffffffffu, tag_ok(m0, tag) && tag_ok(m1, tag) && tag_ok(m2, tag) && tag_ok(m3, tag)));
          write_table(par, false, t7, m0, m1);
          write_table(par, true, t7, m2, m3);
          mbar_arrive(bar_mod2);
        }
      }
      mbar_wait(bar_hpub + (warp & 1) * 8, 0);
      PROF(1, t2 == 0, 24);
#pragma unroll 1
      for (int c = 0; c < 8; c++) {
        const uint32_t off = (warp & 1) * UNIT + c * 2048 + lane * 16;
        uint8_t* dst = g_act + (uint32_t)(rb * 80 + cj * 2) * UNIT + off;
        const uint4 v0 = lds4(stage + off), v1 = lds4(stage + off + 512), v2 = lds4(stage + off + 1024), v3 = lds4(stage + off + 1536);
        stg4(dst, v0); stg4(dst + 512, v1); stg4(dst + 1024, v2); stg4(dst + 1536, v3);
      }
      __syncwarp();
      PROF(1, t2 == 0, 15);
      if (lane == 0) {
        mbar_arrive(bar_pread);
        red_release(&g_cnt_h[rb * 32 + cj * 2 + (warp & 1)], 1);
        PROF(1, t2 == 0, 25);
        prefetch_map(&maps.wg); prefetch_map(&maps.wu); prefetch_map(&maps.wd); prefetch_map(&maps.out);
      }
      __syncwarp();
      if (b < NFFN) {
        mbar_wait(bar_go2, 0);
        const __nv_bfloat16* pg = ((b & 1) ? P.w_up : P.w_gate) + (b >> 1) * 64 + (size_t)t2 * FF;
        const __nv_bfloat16* pd = P.w_down + (size_t)b * 32768 + t2 * 64;
        PROF(2, t2 == 0, 13);
#pragma unroll 1
        for (int i = 0; i < WN; i += WB) {
          uint32_t v[WB];
#pragma unroll
          for (int u = 0; u < WB; u++) {
            const int k = i + u;
            asm volatile("ld.global.cg.L2::128B.u32 %0, [%1];" : "=r"(v[u]) : "l"(k < 16 ? pg + (size_t)k * 64 * FF : pd + (k - 16) * 4096));
          }
#pragma unroll
          for (int u = 1; u < WB; u++) v[0] ^= v[u];
          sts1(par + PAR_SINK + t2 * 4, v[0]);
        }
        PROF(2, t2 == 0, 14);
      }
      const uint32_t tag = epoch % 3 + 1;
      mbar_wait(bar_go, 0);
      bar_sync(4, 64);
      if (warp == 10) {
        const uint32_t* src = g_mod + 2 * DM + cj * 128 + lane * 4;
        const uint2 wr = *reinterpret_cast<const uint2*>(P.w_r + cj * 128 + lane * 4);
        uint4 vga, vsb, vcb, vgb;
        uint32_t n = 0;
        do {
          vga = ld_relaxed4(src); vsb = ld_relaxed4(src + DM); vcb = ld_relaxed4(src + 2 * DM); vgb = ld_relaxed4(src + 3 * DM);
          watchdog(n);
        } while (!__all_sync(0xffffffffu, tag_ok(vga, tag) && tag_ok(vsb, tag) && tag_ok(vcb, tag) && tag_ok(vgb, tag)));
        const float c0 = rbf(1.f + bf_hi(vcb.x)), c1 = rbf(1.f + bf_hi(vcb.y)), c2 = rbf(1.f + bf_hi(vcb.z)), c3 = rbf(1.f + bf_hi(vcb.w));
        const float a0 = c0 * bf_lo(wr.x), a1 = c1 * bf_hi(wr.x), a2 = c2 * bf_lo(wr.y), a3 = c3 * bf_hi(wr.y);
        const uint32_t h0 = pack_bf(a0, a1), h1 = pack_bf(a2, a3);
        const uint32_t t1 = par + PAR_T1 + (lane >> 2) * 64 + (lane & 1) * 32 + (lane & 2) * 2;
        sts1(t1, h0); sts1(t1 + 8, pack_bf(a0 - bf_lo(h0), a1 - bf_hi(h0)));
        sts1(t1 + 16, h1); sts1(t1 + 24, pack_bf(a2 - bf_lo(h1), a3 - bf_hi(h1)));
        const uint32_t tg = par + PAR_SINK + (lane >> 3) * 64 + (lane & 1) * 32 + (lane & 6) * 2;
        sts1(tg, __byte_perm(vga.x, vga.y, 0x7632)); sts1(tg + 16, __byte_perm(vga.z, vga.w, 0x7632));
        sts4(par + PAR_T2 + lane * 32, make_uint4(pack_bf(c0, c1), __byte_perm(vsb.x, vsb.y, 0x7632), __byte_perm(vgb.x, vgb.y, 0x7632), __byte_perm(vga.x, vga.y, 0x7632)));
        sts4(par + PAR_T2 + lane * 32 + 16, make_uint4(pack_bf(c2, c3), __byte_perm(vsb.z, vsb.w, 0x7632), __byte_perm(vgb.z, vgb.w, 0x7632), __byte_perm(vga.z, vga.w, 0x7632)));
      } else {
        const uint4 g = poll4((lane & 8) ? g_mod + 8 - (lane & 1) * 4 : g_mod + 5 * DM + (b >> 4) * 128 + (lane & 7) * 16 + (b & 12), tag);
        sts1(par + PAR_CONST + 60, 0);
        if (lane < 8) sts1(par + PAR_CONST + 16 + lane * 4, (b & 2) ? ((b & 1) ? g.w : g.z) : ((b & 1) ? g.y : g.x));
        else if (lane < 10) sts2(par + PAR_CONST + (lane - 8) * 8, __float_as_uint(untag_sum(g.x, g.y) + untag_sum(g.z, g.w)), epoch);
      }
      __syncwarp();
#pragma unroll 1
      for (int q = 0; q < 32; q++) {
        st_b128(g_xch + ((size_t)b * 8 * 256 + q * 64 + t2) * 4, (epoch & 1) << 16, 0, 0, 0);
        __nanosleep(RSL);
      }
      for (int q = 0; q < 2; q++) st_relaxed4(g_stats + (((rb * 8 + q * 4 + (t2 >> 4)) * 8 + cj) * 16 + (t2 & 15)) * 4, 0, 0, 0, 0);
      if (b < NFFN)
        for (int q = 0; q < 2; q++) st_relaxed4(ypart_slot(b, q * 64 + t2), 0, 0, 0, 0);
      st_relaxed4(g_row + rb * 2 * DM + (t2 >> 5) * DM + cj * 128 + (t2 & 31) * 4, 0, 0, 0, 0);
      __threadfence();
      mbar_arrive(bar_par);
      mbar_wait(bar_gate, 0);
      uint32_t have = 0, n = 0;
      while (true) {
        const uint32_t st = lds1(par + PAR_CONST + 60) >> 7;
        if ((st & 31) != have) {
          const uint32_t* hsrc = g_row + (st & 15) * 2 * DM + t2 * 4;
          uint4 hv[4];
          bool ok = true;
#pragma unroll
          for (int i = 0; i < 4; i++) hv[i] = ld_pairs(hsrc + i * 256);
#pragma unroll
          for (int i = 0; i < 4; i++) {
            sts2(base + ((FT_G >> i * 4) & 15) * UNIT + (warp & 1) * 8192 + 256 + lane * 8, hv[i].x, hv[i].z);
            ok = ok && hv[i].y == tag && hv[i].w == tag;
          }
          have = __all_sync(0xffffffffu, ok) ? st & 31 : 0;
        }
        if ((st ^ have) == 32) break;
        watchdog(n);
      }
      mbar_arrive(bar_sel);
    }
    __syncwarp();
    cluster_arrive();
    {
      const uint32_t tag = epoch % 3 + 1, t3 = tid - 256;
      mbar_wait(bar_win, 0);
      uint2 win = lds2(par + PAR_CONST + 56);
      win.y &= 0x7ff;
      const uint32_t* fsrc = g_row + (win.y >> 7) * 2 * DM + (b >> 4) * 128 + (t3 & 7) * 16 + (b & 6) * 2 + ((b >> 2) & 2);
      const uint32_t* ysrc = ypart_slot(min(t3, NFFN - 1), b);
      uint2 fh = ld_pair(fsrc), fx = ld_pair(fsrc + DM);
      uint4 ya = ld_b128(ysrc);
      const float rwin = __uint_as_float(((int)win.x < 0 ? win.x & 0x7fffffffu : ~win.x) & ~0x1ffu);
      const float rs = rbf(rcp(1.f + __expf(-rbf(rwin))));
      uint32_t n = 0;
      while (__any_sync(0xffffffffu, fh.y != tag || fx.y != tag)) { fh = ld_pair(fsrc); fx = ld_pair(fsrc + DM); watchdog(n); }
      while (true) {
        const bool miss = ((ya.x & 1) | (ya.y & 1) << 1) != tag;
        if (!__any_sync(0xffffffffu, miss)) break;
        if (miss) ya = ld_b128(ysrc);
        watchdog(n);
      }
      PROF(8, t3 == 0, 5);
      float y[8] = {bf_lo(ya.x & ~1u), bf_hi(ya.x), bf_lo(ya.y & ~1u), bf_hi(ya.y), bf_lo(ya.z), bf_hi(ya.z), bf_lo(ya.w), bf_hi(ya.w)};
#pragma unroll
      for (int h = 4; h > 0; h >>= 1) {
        const bool up = lane & (h * 2);
#pragma unroll
        for (int e = 0; e < h; e++) y[e] = (up ? y[e + h] : y[e]) + __shfl_xor_sync(0xffffffffu, up ? y[e] : y[e + h], h * 2);
      }
      y[0] += __shfl_xor_sync(0xffffffffu, y[0], 1);
      if (!(lane & 1)) sts1(par + PAR_RED + 64 + t3 * 2, __float_as_uint(y[0]));
      bar_sync(4, 128);
      if (t3 < 8) {
        float y0 = 0.f;
#pragma unroll
        for (int w7 = 0; w7 < 7; w7++) y0 += __uint_as_float(lds1(par + PAR_RED + 64 + w7 * 32 + t3 * 4));
        const uint32_t gv = lds1(par + PAR_CONST + 16 + t3 * 4);
        const uint32_t upd = hmul2(pack_bf(y0, y0), pack_bf(rs, rs));
        const uint32_t r = hadd2(fx.x, hmul2(__byte_perm(gv, gv, 0x3232), hadd2(fh.x, upd)));
        reinterpret_cast<uint16_t*>(P.out)[(size_t)win.y * DM + (b >> 4) * 128 + t3 * 16 + (b & 15)] = (b & 1) ? r >> 16 : r;
        if (b == 0 && t3 == 0) st_relaxed(&g_epoch, epoch + 1);
      }
      PROF(31, t3 == 0, 36);
    }
    cluster_wait();
  } else {
    const int wg = warp >> 2;

    uint32_t tag;
    auto gemv = [&]() {
      const uint32_t l = fresh_lane(), fr = (l & 7) + (l >> 4) * 8, tq = l & 3, row = base + 2 * GST_BYTES + warp * 2048;
      const uint32_t wa = stage + warp * 4096 + fr * 64 + ((((l >> 3) & 1) ^ ((fr >> 1) & 3)) << 4);
      uint32_t sc[8];
#pragma unroll
      for (int k = 0; k < 8; k++) sc[k] = lds1(row + 128 + k * 16 + tq * 4);
      float d0[4] = {0.f, 0.f, 0.f, 0.f}, d1[4] = {0.f, 0.f, 0.f, 0.f};
      mbar_wait(bar_hw, 0);
#pragma unroll
      for (int ks = 0; ks < 4; ks++) {
        uint32_t w[8];
        ldmatrix4t(wa + ks * 1024, w[0], w[1], w[2], w[3]);
        ldmatrix4t((wa ^ 32) + ks * 1024, w[4], w[5], w[6], w[7]);
        mma16816(d0, w[0], w[1], w[2], w[3], sc[2 * ks], sc[2 * ks + 1]);
        mma16816(d1, w[4], w[5], w[6], w[7], sc[2 * ks], sc[2 * ks + 1]);
      }
      sts1(row + (tq * 8 + (l >> 2)) * 4, __float_as_uint((tq & 2) ? ((tq & 1) ? d1[2] : d1[0]) : ((tq & 1) ? d0[2] : d0[0])));
      bar_sync(1, 256);
      if (warp == 0) {
        float s = 0.f;
#pragma unroll
        for (int w8 = 0; w8 < 8; w8++) s += __uint_as_float(lds1(row + w8 * 2048 + l * 4));
        st_relaxed(g_modp + rank * 2 * DM + (b >> 1) * 32 + l, (__float_as_uint(s) & ~3u) | tag);
      }
      PROF(1, tid == 0, 3);
    };
    {
      uint32_t* const pmod = g_modp + rank * 2 * DM + (b >> 1) * 32 + lane;
      uint32_t* const pln = g_ln1 + (rb * 128 + cj * 16 + warp) * 4;
      const uint32_t cv = ldg_nc1(P.c + rank * 512 + tid * 2);
      const uint32_t epoch = ld_relaxed(&g_epoch);
      if (warp == 0) st_relaxed(pmod, 0);
      if (lane == 0) { st_b128(pln, 0, 0, 0, 0); st_b128(pln + 32, 0, 0, 0, 0); }
      asm volatile("setmaxnreg.inc.sync.aligned.u32 232;");
      bar_sync(1, 320);
      tag = epoch % 3 + 1;
#pragma unroll
      for (int part = 0; part < 3; part++) {
        if (!(part & 1)) {
          const uint32_t xa = base + (2 + part / 2) * GST_BYTES + warp * 2048 + lane * 16;
          mbar_wait(bar_hx + part * 4, 0);
          float s0 = 0.f, s1 = 0.f, q0 = 0.f, q1 = 0.f;
#pragma unroll
          for (int q = 0; q < 4; q++) {
            const uint4 xv = lds4(xa + q * 512);
            const uint32_t u[4] = {xv.x, xv.y, xv.z, xv.w};
#pragma unroll
            for (int e = 0; e < 4; e++) { const float lo = bf_lo(u[e]), hi = bf_hi(u[e]); s0 += lo; s1 += hi; q0 += lo * lo; q1 += hi * hi; }
          }
          s0 += s1; q0 += q1;
#pragma unroll
          for (int o = 16; o > 0; o >>= 1) { s0 += __shfl_xor_sync(0xffffffffu, s0, o); q0 += __shfl_xor_sync(0xffffffffu, q0, o); }
          const float mean = s0 * (1.f / DM);
          float mb, sd;
          ln_scalars(mean, fmaxf(q0 * (1.f / DM) - mean * mean, 0.f), mb, sd);
          uint32_t ih, il;
          split_inv(sd, ih, il);
          if (lane == 0) st_b128(pln + part * 16, pack_bf(mb, mb), ih, il, tag);
          PROF(1, tid == 0 && part == 2, 4);
        } else {
          __syncwarp();
          sts1(base + 2 * GST_BYTES + warp * 2048 + 128 + lane * 4, pack_bf(silu_f(bf_lo(cv)), silu_f(bf_hi(cv))));
          __syncwarp();
          if (!late) gemv();
        }
      }
      cluster_wait();
      if (wg == 1) bar_arrive(2, 256);
    }

    const uint32_t rempty = lane < 2 ? mapa(bempty, lane & 1) : 0;
    constexpr uint32_t GE = NSLOT * 8 + 32;
    float o[64], s[64];
#pragma unroll 1
    for (int ps = 0; ps < 3; ps++) {
      {
        const uint32_t xt = ps == 1 ? XT1 : XT2, wt = ps == 1 ? WT1 : WT2;
        const int nst = ps == 2 ? 28 : 14;
        if (ps == 0) {
          float ga[64], gb[64];
#pragma unroll
          for (int i = 0; i < 64; i++) { ga[i] = 0.f; gb[i] = 0.f; }
          uint32_t a[2][16];
          const uint32_t l = fresh_lane();
          uint32_t fa[4];
#pragma unroll
          for (int kk = 0; kk < 4; kk++) fa[kk] = (base + wg * 8192 + frag_offset(warp)) ^ (kk * 32);
          const uint32_t mt = par + (l & 3) * 16;
          auto fetch = [&](int i, uint32_t (&f)[16], uint32_t z) {
            mbar_wait(xfull + (i & 3) * 8, i >> 2);
#pragma unroll
            for (int kk = 0; kk < 4; kk++) ldmatrix4(fa[kk] + (i & 3) * GST_BYTES + z, f[4 * kk], f[4 * kk + 1], f[4 * kk + 2], f[4 * kk + 3]);
          };
          const bool oddw = warp & 2;
          uint4 r0, r1;
          {
            const uint32_t t7 = (warp & 1) * 64 + (l >> 4) * 32 + (l & 15);
            const uint32_t* pm = g_modp + wg * DM + ((cj * 128 + t7 * 4) & (DM - 1));
            const uint32_t* pr = g_ln1 + (rb * 128 + warp * 16 + (l >> 2)) * 4;
            uint4 m0 = make_uint4(tag, tag, tag, tag), m1 = m0;
            if (late) gemv();
            if (!oddw) { m0 = ld_relaxed4(pm); m1 = ld_relaxed4(pm + 2 * DM); }
            r0 = ld_b128(pr); r1 = ld_b128(pr + 32);
            fetch(0, a[0], 0); fetch(1, a[1], 0);
            uint32_t n = 0;
            bool written = false;
#pragma unroll 1
            while (true) {
              uint32_t miss;
              asm volatile("{ .reg .pred p0, p1, p2, p3; .reg .b32 t, u;\n"
                           "lop3.b32 t, %1, %2, %19, 0x7e; lop3.b32 u, %3, %4, %19, 0x7e; or.b32 t, t, u; and.b32 t, t, 3; setp.ne.u32 p0, t, 0;\n"
                           "lop3.b32 t, %5, %6, %19, 0x7e; lop3.b32 u, %7, %8, %19, 0x7e; or.b32 t, t, u; and.b32 t, t, 3; setp.ne.u32 p1, t, 0;\n"
                           "setp.ne.u32 p2, %12, %19; setp.ne.u32 p3, %16, %19;\n"
                           "@p0 ld.relaxed.gpu.global.v4.u32 {%1, %2, %3, %4}, [%17];\n"
                           "@p1 ld.relaxed.gpu.global.v4.u32 {%5, %6, %7, %8}, [%17 + 8192];\n"
                           "@p2 ld.relaxed.gpu.global.v4.u32 {%9, %10, %11, %12}, [%18];\n"
                           "@p3 ld.relaxed.gpu.global.v4.u32 {%13, %14, %15, %16}, [%18 + 128];\n"
                           "or.pred p0, p0, p1; or.pred p2, p2, p3; vote.sync.any.pred p0, p0, 0xffffffff; vote.sync.any.pred p2, p2, 0xffffffff;\n"
                           "selp.u32 t, 1, 0, p0; selp.u32 u, 2, 0, p2; or.b32 %0, t, u; }"
                           : "=r"(miss), "+r"(m0.x), "+r"(m0.y), "+r"(m0.z), "+r"(m0.w), "+r"(m1.x), "+r"(m1.y), "+r"(m1.z), "+r"(m1.w),
                             "+r"(r0.x), "+r"(r0.y), "+r"(r0.z), "+r"(r0.w), "+r"(r1.x), "+r"(r1.y), "+r"(r1.z), "+r"(r1.w)
                           : "l"(pm), "l"(pr), "r"(tag) : "memory");
              if (!(miss & 1) && !written) {
                written = true;
                if (!oddw) write_table(par, wg, t7, m0, m1);
                mbar_arrive(bar_mod);
              }
              if (!miss) break;
              watchdog(n);
            }
          }
          const uint32_t zero = r0.w ^ tag;
          auto normalize = [&](uint32_t (&f)[16]) {
#pragma unroll
            for (int k = 0; k < 16; k += 2) { f[k] = ln_norm(f[k], r0.x, r0.y, r0.z); f[k + 1] = ln_norm(f[k + 1], r1.x, r1.y, r1.z); }
          };
          auto modulate = [&](int i, uint32_t (&f)[16]) {
#pragma unroll
            for (int kk = 0; kk < 4; kk++) {
              const uint4 m = lds4(mt + slice_of(i) * 256 + kk * 64);
              f[4 * kk] = hfma2(f[4 * kk], m.x, m.z); f[4 * kk + 1] = hfma2(f[4 * kk + 1], m.x, m.z);
              f[4 * kk + 2] = hfma2(f[4 * kk + 2], m.y, m.w); f[4 * kk + 3] = hfma2(f[4 * kk + 3], m.y, m.w);
            }
            keep(f);
            mbar_arrive_pred(xempty + (i & 3) * 8, l == 0);
          };
          auto publish = [&](int u, uint32_t (&f)[16]) {
#pragma unroll
            for (int kk = 0; kk < 4; kk++) stmatrix4(fa[kk] + OFF_STAGE + u * UNIT, f[4 * kk], f[4 * kk + 1], f[4 * kk + 2], f[4 * kk + 3]);
            __syncwarp();
            mbar_arrive_pred(bar_hpub + u * 8, l == 0);
          };
          auto multiply = [&](int i, uint32_t (&f)[16]) {
            mbar_wait(gfull + (i & 3) * 8, i >> 2);
            const uint64_t db = make_desc(base + (i & 3) * GST_BYTES + UNIT, 8192, 1024);
            wg_fence();
#pragma unroll
            for (int kk = 0; kk < 4; kk++) mma256_rs(ga, gb, f[4 * kk], f[4 * kk + 1], f[4 * kk + 2], f[4 * kk + 3], db + kk * 128);
            wg_commit();
          };
          auto next = [&](int i, uint32_t (&f)[16]) {
            wg_wait<1>();
            mbar_arrive_cl(rempty, GE + ((i + 2) & 3) * 8);
            uint32_t z = zero;
#pragma unroll
            for (int k = 0; k < 16; k += 2) asm volatile("lop3.b32 %0, %1, %2, %0, 0xA8;" : "+r"(z) : "r"(f[k]), "r"(f[k + 1]));
            fetch(i, f, z);
            normalize(f);
            if (i == 3) { keep(f); mbar_wait(bar_mod2, 0); }
            modulate(i, f); multiply(i, f);
          };
          normalize(a[0]);
          keep(a[0]); keep(a[1]);
          mbar_wait(bar_mod, 0);
          PROF(1, tid == 0, 2);
          modulate(0, a[0]); multiply(0, a[0]); publish(0, a[0]);
          keep(a[1]);
          normalize(a[1]);
          modulate(1, a[1]); multiply(1, a[1]);
#pragma unroll 1
          for (int i = 2; i < NRS; i += 2) {
            next(i, a[0]);
            next(i + 1, a[1]);
            if (i == 2) publish(1, a[1]);
          }
          wg_wait<1>();
          mbar_arrive_cl(rempty, GE + ((NRS + 2) & 3) * 8);
#pragma unroll 1
          for (int i = NRS; i < 14; i++) {
            mbar_wait(xfull + (i & 3) * 8, (i >> 2) & 1);
            mbar_wait(gfull + (i & 3) * 8, (i >> 2) & 1);
            const uint32_t xa = base + (i & 3) * GST_BYTES;
            const uint64_t da = make_desc(xa + wg * 8192, 16, 1024), db = make_desc(xa + UNIT, 8192, 1024);
            if (i == 13) bar_sync(2 + wg, 256);
            wg_fence();
#pragma unroll
            for (int kk = 0; kk < 4; kk++) mma256_ss(ga, gb, da + kk * 2, db + kk * 128, 1);
            wg_commit();
            if (i == 13) bar_arrive(3 - wg, 256);
            wg_wait<1>();
            uint32_t z = zero;
#pragma unroll
            for (int k = 0; k < 16; k += 2) asm volatile("lop3.b32 %0, %1, %2, %0, 0xA8;" : "+r"(z) : "r"(a[1][k]), "r"(a[1][k + 1]));
            mbar_arrive_cl(rempty, GE + ((i + 3) & 3) * 8 + z);
            mbar_arrive_pred(xempty + ((i + 3) & 3) * 8, l == 0 && i != NRS);
          }
          mbar_wait(xfull + 16, 1);
          wg_wait<0>();
          keep(ga); keep(gb);
#pragma unroll
          for (int i = 0; i < 64; i++) {
            asm volatile("mov.b32 %0, %1;" : "=f"(s[i]) : "f"(ga[i]));
            asm volatile("mov.b32 %0, %1;" : "=f"(o[i]) : "f"(gb[i]));
          }
        } else {
          float ga[64], gb[64];
#pragma unroll
          for (int i = 0; i < 64; i++) {
            asm volatile("mov.b32 %0, %1;" : "=f"(ga[i]) : "f"(s[i]));
            asm volatile("mov.b32 %0, %1;" : "=f"(gb[i]) : "f"(o[i]));
          }
#pragma unroll 1
          for (int i = 0; i < nst; i++) {
            mbar_wait(gfull + (i & 3) * 8, (i >> 2) & 1);
            const uint64_t da = make_desc(base + unit_of(xt, i & 3) + wg * 8192, 16, 1024), db = make_desc(base + unit_of(wt, i & 3), 8192, 1024);
            if (i == nst - 1) bar_sync(2 + wg, 256);
            wg_fence();
#pragma unroll
            for (int kk = 0; kk < 4; kk++) mma256_ss(ga, gb, da + kk * 2, db + kk * 128, kk ? 1 : i);
            wg_commit();
            if (i == nst - 1) bar_arrive(3 - wg, 256);
            wg_wait<1>();
            mbar_arrive_cl(rempty, GE + ((i + 3) & 3) * 8, i != 0);
            PROF(4, tid == 0 && (i & 3) == 0, 40 + (ps - 1) * 4 + i / 4);
          }
          wg_wait<0>();
          keep(ga); keep(gb);
#pragma unroll
          for (int i = 0; i < 64; i++) {
            asm volatile("mov.b32 %0, %1;" : "=f"(s[i]) : "f"(ga[i]));
            asm volatile("mov.b32 %0, %1;" : "=f"(o[i]) : "f"(gb[i]));
          }
        }
        mbar_arrive_cl(rempty, GE + (ps == 2 ? 24 : 8));
        if (ps == 2) break;
      }
      const uint32_t qw = base + wg * 8192, qt = QT >> (16 * ps), at = ps ? AT1 : AT0;
      {
        const uint32_t wt = ps ? WT1 : WT0;
        const uint64_t da0 = make_desc(qw + unit_of(qt, 2), 16, 1024), da1 = make_desc(qw + unit_of(qt, 3), 16, 1024);
        const uint64_t db0 = make_desc(base + unit_of(wt, 2), 8192, 1024), db1 = make_desc(base + unit_of(wt, 3), 8192, 1024);
        mbar_wait(gfull + 16, 1);
        bar_sync(2 + wg, 256);
        wg_fence();
#pragma unroll
        for (int kk = 0; kk < 4; kk++) mma_ss<1>(s, da0 + kk * 2, db0 + kk * 128, 1);
        wg_commit();
        mbar_wait(xfull + 24, 1);
        mbar_wait(gfull + 24, 1);
        wg_fence();
#pragma unroll
        for (int kk = 0; kk < 4; kk++) mma_ss<1>(s, da1 + kk * 2, db1 + kk * 128, 1);
        wg_commit();
        bar_arrive(3 - wg, 256);
        mbar_wait(ps == 0 ? bar_pread : bar_ofree + 8, 0);
        wg_wait<0>();
        keep(s);
        PROF(2, tid == 0, 8 + ps * 8);
        uint32_t q[32];
        pack_p(s, q);
#pragma unroll
        for (int i = 0; i < 4; i++) stmatrix4((qw + unit_of(qt, 0) + frag_offset(warp)) ^ (i << 5), q[4 * i], q[4 * i + 1], q[4 * i + 2], q[4 * i + 3]);
        keep(q);
        bar_sync(2 + wg, 256);
        wg_fence();
#pragma unroll
        for (int kk = 0; kk < 8; kk++) mma_ss<1>(o, (kk < 4 ? da0 : da1) + (kk & 3) * 2, (kk < 4 ? db0 : db1) + UNIT / 16 + (kk & 3) * 128, 1);
        wg_commit();
        mbar_wait(bfull, 0);
        wg_fence();
        const uint64_t dk = make_desc(base + unit_of(at, 0), 16, 1024);
#pragma unroll
        for (int kk = 0; kk < 8; kk++) mma_rs<0>(s, q[4 * kk], q[4 * kk + 1], q[4 * kk + 2], q[4 * kk + 3], dk + (kk >> 2) * 1024 + (kk & 3) * 2, kk != 0);
        wg_commit();
        bar_arrive(3 - wg, 256);
#pragma unroll
        for (int i = 4; i < 8; i++) stmatrix4((qw + unit_of(qt, 1) + frag_offset(warp)) ^ ((i & 3) << 5), q[4 * i], q[4 * i + 1], q[4 * i + 2], q[4 * i + 3]);
        wg_wait<1>();
        keep(o);
        mbar_arrive_cl(rempty, GE + 16);
        mbar_arrive_cl(rempty, GE + 24);
        store_chunk<0>(o, qw + unit_of(qt, 2) + frag_offset(warp));
        store_chunk<1>(o, qw + unit_of(qt, 3) + frag_offset(warp));
        wg_wait<0>();
        keep(s);
        mbar_arrive_cl(rempty, 0);
      }
      PROF(4, tid == 0 && ps == 1, 61);
      float l0 = 0.f, l1 = 0.f, f0 = 0.f, f1 = 0.f;
      auto step = [&](auto odd_c, const int j, uint32_t (&pw)[32], uint32_t (&pr)[32]) {
        constexpr bool ODD = decltype(odd_c)::value;
        const bool first = !ODD && (j & 2) == 0, last = ODD && j == 7;
        const uint32_t ph = (j >> 1) & 1;
        float i0, i1, a0, a1;
        const bool so = !ODD && j == 4;
        if (so) { i0 = inv_quad_sum(l0); i1 = inv_quad_sum(l1); l0 = 0.f; l1 = 0.f; }
        if (first) {
          int m0 = max(__float_as_int(s[0]), __float_as_int(s[1])), m1 = max(__float_as_int(s[2]), __float_as_int(s[3]));
#pragma unroll
          for (int i = 1; i < 16; i++) {
            m0 = __vimax3_s32(m0, __float_as_int(s[4 * i]), __float_as_int(s[4 * i + 1]));
            m1 = __vimax3_s32(m1, __float_as_int(s[4 * i + 2]), __float_as_int(s[4 * i + 3]));
          }
          m0 = max(m0, __shfl_xor_sync(0xffffffffu, m0, 1)); m1 = max(m1, __shfl_xor_sync(0xffffffffu, m1, 1));
          m0 = max(m0, __shfl_xor_sync(0xffffffffu, m0, 2)); m1 = max(m1, __shfl_xor_sync(0xffffffffu, m1, 2));
          f0 = fmaf(__int_as_float(m0), SCL2, BIAS); f1 = fmaf(__int_as_float(m1), SCL2, BIAS);
        }
        bool redo = false;
        while (true) {
          if (redo) {
            float m0 = fmaxf(s[0], s[1]), m1 = fmaxf(s[2], s[3]);
#pragma unroll
            for (int i = 1; i < 16; i++) { m0 = fmaxf(m0, fmaxf(s[4 * i], s[4 * i + 1])); m1 = fmaxf(m1, fmaxf(s[4 * i + 2], s[4 * i + 3])); }
            m0 = fmaxf(m0, __shfl_xor_sync(0xffffffffu, m0, 1)); m1 = fmaxf(m1, __shfl_xor_sync(0xffffffffu, m1, 1));
            m0 = fmaxf(m0, __shfl_xor_sync(0xffffffffu, m0, 2)); m1 = fmaxf(m1, __shfl_xor_sync(0xffffffffu, m1, 2));
            m0 = fmaf(m0, SCL2, BIAS); m1 = fmaf(m1, SCL2, BIAS);
            if (!first) {
              m0 = fmaxf(m0, f0); m1 = fmaxf(m1, f1);
              const float c0 = ex2(f0 - m0), c1 = ex2(f1 - m1);
              l0 *= c0; l1 *= c1;
              wg_wait<0>();
              keep(o);
#pragma unroll
              for (int i = 0; i < 16; i++) { o[4 * i] *= c0; o[4 * i + 1] *= c0; o[4 * i + 2] *= c1; o[4 * i + 3] *= c1; }
            }
            f0 = m0; f1 = m1;
          }
          float b0 = 0.f, b1 = 0.f;
          a0 = 0.f; a1 = 0.f;
#pragma unroll
          for (int i = 0; i < 16; i++) {
            const float e0 = ex2(fmaf(s[4 * i], SCL2, -f0)), e1 = ex2(fmaf(s[4 * i + 1], SCL2, -f0));
            const float e2 = ex2(fmaf(s[4 * i + 2], SCL2, -f1)), e3 = ex2(fmaf(s[4 * i + 3], SCL2, -f1));
            a0 += e0; b0 += e1; a1 += e2; b1 += e3;
            pw[2 * i] = pack_bf(e0, e1); pw[2 * i + 1] = pack_bf(e2, e3);
            if (i == VREL) {
#pragma unroll
              for (int k = 0; k < 2 * VREL + 2; k++) asm volatile("" : "+r"(pw[k])::"memory");
              mbar_wait(bar_mod, 0);
              wg_wait<0>();
              mbar_arrive_cl(rempty, ODD ? 16 : 0, !redo && (ODD || j));
#pragma unroll
              for (int k = 4 * VREL + 4; k < 64; k++) asm volatile("" : "+f"(s[k])::"memory");
            }
          }
          a0 += b0; a1 += b1;
          if (redo) break;
          redo = __any_sync(0xffffffffu, !(a0 + a1 < 1.f));
          if (!redo) break;
        }
        l0 += a0; l1 += a1;
        keep(pw);
        keep(o);
        if (so) store_chunk<0>(o, i0, i1, qw + unit_of(qt, 0) + frag_offset(warp));
        keep(o);
        if (j == (ODD ? 5 : 0)) { fence_async_smem(); if (ODD) mbar_arrive(bar_ofull + wg * 8); }
        mbar_wait(bfull + (ODD ? 24 : 8), ph);
        bar_sync(2 + wg, 256);
        if (!last) {
          const uint32_t qn = qt >> (j >= 3 ? 8 : 0);
          wg_fence();
          issue_qk(s, qw + unit_of(qn, 0), qw + unit_of(qn, 1), base + unit_of(at, ODD ? 3 : 1));
          wg_commit();
          mbar_wait(bfull + (ODD ? 0 : 16), ODD ? ph ^ 1 : ph);
        }
        if (so) { store_chunk<1>(o, i0, i1, qw + unit_of(qt, 1) + frag_offset(warp)); keep(o); }
        wg_fence();
        issue_pv(o, pw, base + unit_of(at, ODD ? (last ? 3 : 0) : 2), !first);
        wg_commit();
        bar_arrive(3 - wg, 256);
        wg_wait<1>();
        keep(s);
        mbar_arrive_cl(rempty, ODD ? 24 : 8, !last);
        PROF(4, tid == 0 && ps == 1, 51 + j);
      };
      uint32_t pa[32], pb[32];
#pragma unroll 1
      for (int j = 0; j < 8; j += 2) {
        step(std::false_type{}, j, pa, pb);
        step(std::true_type{}, j + 1, pb, pa);
      }
      {
        const float i0 = inv_quad_sum(l0), i1 = inv_quad_sum(l1);
        wg_wait<0>();
        keep(o);
        mbar_arrive_cl(rempty, 24);
        store_chunk<0>(o, i0, i1, qw + unit_of(qt, 2) + frag_offset(warp));
        store_chunk<1>(o, i0, i1, qw + unit_of(qt, 3) + frag_offset(warp));
        fence_async_smem();
        mbar_arrive(bar_ofull + 16 + wg * 8);
      }
      PROF(2, tid == 0, 10 + ps * 8);
    }

    const int ln = fresh_lane(), g = ln >> 2, tq = ln & 3, ct = warp * 32 + ln;
    const bool lane0 = ln == 0;
    const int lrow0 = warp * 16 + g;
    const uint32_t res = base + OFF_RES, trow = res + wg * 8192 + frag_offset(warp);
    uint32_t xr[32];
    uint4 sv[4], own;
    uint32_t* const sg = g_stats + (rb * 8 + warp) * 512 + g * 4;
    uint32_t* sp[4];
#pragma unroll
    for (int k = 0; k < 4; k++) sp[k] = sg + (tq & 1) * 32 + (((tq >> 1) ^ (cj >> 2)) * 4 + (k ^ (cj & 3))) * 64;
    {
      const uint64_t da = make_desc(base + wg * 8192, 16, 1024), db = make_desc(base, 8192, 1024);
      constexpr int U = UNIT / 16;
#define HALF_STAGE(acc, xu, wu) _Pragma("unroll") for (int kk = 0; kk < 4; kk++) mma_ss<1>(acc, da + (xu) * U + kk * 2, db + (wu) * U + kk * 128, 1)
      PROF(10, ct == PT, 19); STAMP(0);
      cluster_arrive();
      mbar_wait(gfull, 1);
      mbar_wait(gfull + 8, 1);
      bar_sync(2 + wg, 256);
      wg_fence();
      HALF_STAGE(o, 7, 1);
      HALF_STAGE(o, 8, 3);
      wg_commit();
      STAMP(16);
      mbar_wait(gfull + 16, 1);
      STAMP(17);
      wg_fence();
      HALF_STAGE(o, 6, 11);
      wg_commit();
      bar_arrive(3 - wg, 256);
      mbar_wait(bar_par, 0);
      uint32_t* xo = g_xch + ((size_t)b * 8 * 256 + ct) * 4;
      const uint32_t* xi = g_xch + ((size_t)(b ^ 2) * 8 * 256 + ct) * 4;
      const uint32_t par1 = (~lds1(par + PAR_CONST + 4) & 1) << 16;
      wg_wait<1>();
      mbar_arrive_pred(bar_rel, lane0);
      wg_wait<0>();
      keep(o);
      mbar_arrive_pred(bar_ring, lane0);
      PROF(8, ct == PT, 20); STAMP(1);
#define SEND(i) st_b128(xo + (i) * 1024, (pack_bf(o[8 * (i)], o[8 * (i) + 1]) & ~0x10000u) | par1, pack_bf(o[8 * (i) + 2], o[8 * (i) + 3]), \
                        pack_bf(o[8 * (i) + 4], o[8 * (i) + 5]), pack_bf(o[8 * (i) + 6], o[8 * (i) + 7]))
#pragma unroll
      for (int i = 0; i < NS1; i++) SEND(i);
      PROF(8, ct == PT, 21); STAMP(2);
      bar_sync(2 + wg, 256);
      wg_fence();
      HALF_STAGE(s, 7, 0);
      HALF_STAGE(s, 8, 2);
      HALF_STAGE(s, 6, 10);
      wg_commit();
      bar_arrive(3 - wg, 256);
      STAMP(18);
      mbar_wait(gfull + 24, 1);
#pragma unroll
      for (int i = NS1; i < 8; i++) SEND(i);
      uint4 v[8];
      STAMP(19);
      mbar_wait(bar_xres, 0);
      wg_wait<0>();
      mbar_arrive_pred(bar_ring + 8, lane0);
      bar_sync(2 + wg, 256);
      STAMP(20);
#pragma unroll
      for (int i = 0; i < LD2; i++) v[i] = ld_b128(xi + i * 1024);
      mbar_wait(bar_xres, 0);
      wg_fence();
      HALF_STAGE(s, 9, 4);
      wg_commit();
      mbar_wait(bar_rx, 0);
      wg_fence();
      HALF_STAGE(s, 1, 5);
      wg_commit();
      bar_arrive(3 - wg, 256);
      STAMP(21);
#pragma unroll
      for (int i = LD2; i < 8; i++) v[i] = ld_b128(xi + i * 1024);
      mbar_wait(bar_xres, 0);
      wg_wait<0>();
      keep(s);
      mbar_arrive_pred(bar_ring + 16, lane0);
      PROF(10, ct == PT, 23); STAMP(4);
#pragma unroll
      for (int i = 0; i < 16; i += 2) ldmatrix4((trow ^ ((i & 7) << 4)) + (i >> 3) * 16384, xr[2 * i], xr[2 * i + 1], xr[2 * i + 2], xr[2 * i + 3]);
      uint32_t ga[16];
      uint4 bw[8];
#pragma unroll
      for (int i = 0; i < 8; i++) {
        if (!(i & 1)) {
          const uint4 t = lds4(par + PAR_SINK + i * 32 + tq * 16);
          ga[2 * i] = t.x; ga[2 * i + 1] = t.y; ga[2 * i + 2] = t.z; ga[2 * i + 3] = t.w;
        }
        bw[i] = lds4(par + PAR_T1 + i * 64 + tq * 16);
        if (!(g & 1)) { bw[i].x = 0x3f803f80u; bw[i].y = 0x3f803f80u; }
      }
      uint32_t pk[32];
      pack_p(s, pk);
      const uint32_t par2 = (~lds1(par + PAR_CONST + 12) & 1) << 16;
      {
        uint32_t n = 0, miss;
        do {
          miss = 0;
#pragma unroll
          for (int i = 0; i < 8; i++) miss |= v[i].x ^ par2;
          miss = __any_sync(0xffffffffu, miss & 0x10000u);
          if (miss) {
#pragma unroll
            for (int i = 0; i < 8; i++)
              asm volatile("{ .reg .pred p; .reg .b32 t; xor.b32 t, %0, %5; and.b32 t, t, 0x10000; setp.ne.u32 p, t, 0;\n"
                           "@p ld.relaxed.gpu.global.v4.u32 {%0, %1, %2, %3}, [%4]; }"
                           : "+r"(v[i].x), "+r"(v[i].y), "+r"(v[i].z), "+r"(v[i].w) : "l"(xi + i * 1024), "r"(par1) : "memory");
          }
          watchdog(n);
        } while (miss);
      }
      PROF(8, ct == PT, 22); STAMP(3);
      float ds[4] = {0.f, 0.f, 0.f, 0.f}, dl[4] = {0.f, 0.f, 0.f, 0.f}, q0[4] = {0.f, 0.f, 0.f, 0.f}, q1[4] = {0.f, 0.f, 0.f, 0.f};
#pragma unroll
      for (int i = 0; i < 8; i++) {
        const uint32_t u0 = hfma2(ga[2 * i], hadd2(pk[4 * i], v[i].x & ~0x10000u), xr[4 * i]);
        const uint32_t u1 = hfma2(ga[2 * i], hadd2(pk[4 * i + 1], v[i].y), xr[4 * i + 1]);
        const uint32_t u2 = hfma2(ga[2 * i + 1], hadd2(pk[4 * i + 2], v[i].z), xr[4 * i + 2]);
        const uint32_t u3 = hfma2(ga[2 * i + 1], hadd2(pk[4 * i + 3], v[i].w), xr[4 * i + 3]);
        xr[4 * i] = u0; xr[4 * i + 1] = u1; xr[4 * i + 2] = u2; xr[4 * i + 3] = u3;
        mma16816(ds, u0, u1, u2, u3, bw[i].x, bw[i].y);
        mma16816(dl, u0, u1, u2, u3, bw[i].z, bw[i].w);
        mma16816(q0, u0, u1, u2, u3, u0, u2);
        mma16816(q1, u0, u1, u2, u3, u1, u3);
      }
      const float sqa = (g & 1) ? q0[1] : q0[0], sqb = (g & 1) ? q1[3] : q1[2], dta = ds[1] + dl[1], dtb = ds[3] + dl[3];
      if (tq == (g >> 1)) {
        st_b128(sg + cj * 64, __float_as_uint(ds[0]), __float_as_uint(sqa), __float_as_uint(dta), tag);
        st_b128(sg + cj * 64 + 32, __float_as_uint(ds[2]), __float_as_uint(sqb), __float_as_uint(dtb), tag);
      }
#pragma unroll
      for (int k = 0; k < 4; k++) sv[k] = ld_b128(sp[k]);
      mbar_wait(bar_xres, 0);
      const float sqc = __shfl_sync(0xffffffffu, sqa, g * 4 + (g >> 1)), sqd = __shfl_sync(0xffffffffu, sqb, g * 4 + (g >> 1));
      own = (tq & 1) ? make_uint4(__float_as_uint(ds[2]), __float_as_uint(sqd), __float_as_uint(dtb), tag)
                     : make_uint4(__float_as_uint(ds[0]), __float_as_uint(sqc), __float_as_uint(dta), tag);
    }
    PROF(8, ct == PT, 29); STAMP(5);
    uint32_t mm, ih, il;
    float rbest;
    uint32_t wf[128];
    const uint32_t frow = (ln & 7) + (ln >> 4) * 8;
    const uint32_t wfo = base + (warp & 1) * 8192 + frow * 64 + ((((ln >> 3) & 1) ^ ((frow >> 1) & 3)) << 4);
#define LOAD_WF(m) _Pragma("unroll") for (int f = 0; f < 16; f++) {                                                   \
      const int r = ((f >> 1) * 4 + (m) * 2 + (f & 1)) * 4;                                                           \
      ldmatrix4t(((wfo + unit_of((m) ? FT_U : FT_G, warp >> 1)) ^ ((f & 1) * 32)) + (f >> 1) * 1024, wf[r], wf[r + 1], wf[r + 2], wf[r + 3]); \
    }
    bool early;
    {
#pragma unroll
      for (int i = 0; i < 16; i += 2) stmatrix4((trow ^ ((i & 7) << 4)) + (i >> 3) * 16384, xr[2 * i], xr[2 * i + 1], xr[2 * i + 2], xr[2 * i + 3]);
      const uint4 cst = lds4(par + PAR_CONST);
      const float A1 = __uint_as_float(cst.x), A2 = __uint_as_float(cst.z);
      uint32_t n = 0;
      early = false;
#pragma unroll 1
      while (true) {
        if (!early && (b >= NFFN || __all_sync(0xffffffffu, mbar_test(bar_box + (warp >> 1) * 8, 0)))) {
          early = true;
          LOAD_WF(0);
          __syncwarp();
          mbar_arrive_pred(bar_gate, lane0);
        }
        uint32_t miss;
        asm volatile("{ .reg .pred p0, p1, p2, p3; .reg .b64 u, v; .reg .b128 w;\n"
                     "setp.ge.u32 p0, %22, 2; setp.ne.and.u32 p0, %4, %21, p0; setp.ne.u32 p1, %8, %21; setp.ne.u32 p2, %12, %21; setp.ne.u32 p3, %16, %21;\n"
                     "@p0 ld.relaxed.gpu.global.v4.u32 {%1, %2, %3, %4}, [%17];\n"
                     "@p1 ld.relaxed.gpu.global.v4.u32 {%5, %6, %7, %8}, [%18];\n"
                     "@p2 ld.relaxed.gpu.global.v4.u32 {%9, %10, %11, %12}, [%19];\n"
                     "@p3 ld.relaxed.gpu.global.v4.u32 {%13, %14, %15, %16}, [%20];\n"
                     "or.pred p0, p0, p1; or.pred p2, p2, p3; or.pred p0, p0, p2; vote.sync.any.pred p0, p0, 0xffffffff; selp.u32 %0, 1, 0, p0; }"
                     : "=r"(miss), "+r"(sv[0].x), "+r"(sv[0].y), "+r"(sv[0].z), "+r"(sv[0].w), "+r"(sv[1].x), "+r"(sv[1].y), "+r"(sv[1].z), "+r"(sv[1].w),
                       "+r"(sv[2].x), "+r"(sv[2].y), "+r"(sv[2].z), "+r"(sv[2].w), "+r"(sv[3].x), "+r"(sv[3].y), "+r"(sv[3].z), "+r"(sv[3].w)
                     : "l"(sp[0]), "l"(sp[1]), "l"(sp[2]), "l"(sp[3]), "r"(tag), "r"(tq) : "memory");
        if (!miss) break;
        watchdog(n);
      }
      const uint4 v0 = tq < 2 ? own : sv[0], v1 = sv[1], v2 = sv[2], v3 = sv[3];
      PROF(8, ct == PT, 30); STAMP(6);
      float su = (__uint_as_float(v0.x) + __uint_as_float(v1.x)) + (__uint_as_float(v2.x) + __uint_as_float(v3.x));
      float sq = (__uint_as_float(v0.y) + __uint_as_float(v1.y)) + (__uint_as_float(v2.y) + __uint_as_float(v3.y));
      float dt = (__uint_as_float(v0.z) + __uint_as_float(v1.z)) + (__uint_as_float(v2.z) + __uint_as_float(v3.z));
      su += __shfl_xor_sync(0xffffffffu, su, 2); sq += __shfl_xor_sync(0xffffffffu, sq, 2); dt += __shfl_xor_sync(0xffffffffu, dt, 2);
      const float m = su * (1.f / DM);
      float mb, sd;
      ln_scalars(m, fmaxf(sq * (1.f / DM) - m * m, 0.f), mb, sd);
      const float inv = rcp(sd);
      rbest = (dt - mb * A1) * inv + A2;
      mm = pack_bf(mb, mb);
      ih = pack_bf(inv, inv);
      const float lo = inv - bf_lo(ih);
      il = pack_bf(lo, lo);
    }
    int ibest;
    {
      const uint32_t bits = __float_as_uint(rbest);
      const uint32_t key = (((int)bits < 0 ? ~bits : bits | 0x80000000u) & ~0x1ffu) | ((127 - lrow0 - (tq & 1) * 8) << 2) | tag;
      sts1(par + PAR_RED + warp * 4, __reduce_max_sync(0xffffffffu, key));
      PROF(8, ct == PT, 38); STAMP(7);
      bar_sync(1, 256);
      const uint4 ka = lds4(par + PAR_RED), kb = lds4(par + PAR_RED + 16);
      const uint32_t k2 = max(max(max(ka.x, ka.y), max(ka.z, ka.w)), max(max(kb.x, kb.y), max(kb.z, kb.w)));
      if (ct < CR && cj == 0) st_relaxed(g_cand + ct * 512 + rb * CS, k2);
      ibest = 127 - ((k2 >> 2) & 127);
    }
    PROF(8, ct == PT, 39); STAMP(8);
    if ((ibest >> 4) == warp) {
      const int src = (ibest & 7) * 4 + ((ibest >> 3) & 1), ch = g * 2;
      const uint32_t cm = __shfl_sync(0xffffffffu, mm, src), ch_ = __shfl_sync(0xffffffffu, ih, src), cl = __shfl_sync(0xffffffffu, il, src);
      const uint32_t xa = res + (ch >> 3) * 16384 + ibest * 128 + (((ch & 7) ^ (ibest & 7)) << 4) + tq * 4;
      const uint32_t x0 = lds1(xa), x1 = lds1(xa ^ 16);
      const uint2 p0 = lds2(par + PAR_T2 + ch * 64 + tq * 16), p1 = lds2(par + PAR_T2 + ch * 64 + 64 + tq * 16);
      uint32_t* dst = g_row + rb * 2 * DM + cj * 128 + ln * 4;
      st_pairs(dst, ln_mod(x0, cm, ch_, cl, p0.x, p0.y), ln_mod(x1, cm, ch_, cl, p1.x, p1.y), tag);
      st_pairs(dst + DM, x0, x1, tag);
      __syncwarp();
    }
    PROF(8, ct == PT, 37); STAMP(9);
    uint32_t wd[64];
    const uint32_t wda = base + unit_of(FT_D, warp >> 1) + (warp & 1) * 8192 + frow * 128 + ((((ln >> 3) & 1) ^ (ln & 7)) << 4);
#define LOAD_WD(f) ldmatrix4t((wda ^ ((((f) >> 1) & 3) * 32)) + ((f) >> 3) * 4096 + ((f) & 1) * 2048, wd[4 * (f)], wd[4 * (f) + 1], wd[4 * (f) + 2], wd[4 * (f) + 3])
    if (!early) {
      if (b < NFFN) mbar_wait(bar_box + (warp >> 1) * 8, 0);
      LOAD_WF(0);
      __syncwarp();
      mbar_arrive_pred(bar_gate, lane0);
    }
    if (b < NFFN) {
      const uint32_t own = base + unit_of(FT_G, warp >> 1) + (warp & 1) * 8192;
      mbar_wait(bar_box + (4 + (warp >> 1)) * 8, 0);
      LOAD_WF(1);
      uint32_t* const ydst = ypart_slot(b, warp * 16 + (tq & 1) * 8 + g);
      PROF(8, ct == PT, 31); STAMP(10);
      bool wdok;
      {
        uint32_t n = 0;
        while (!(wdok = __all_sync(0xffffffffu, mbar_test(bar_box + (8 + (warp >> 1)) * 8, 0))) && !__all_sync(0xffffffffu, mbar_test(bar_sel, 0))) watchdog(n);
      }
      if (wdok) {
#pragma unroll
        for (int f = 0; f < 16; f++) LOAD_WD(f);
      }
      STAMP(11);
      mbar_wait(bar_sel, 0);
      PROF(8, ct == PT, 33); STAMP(12);
      float d[8][4];
#pragma unroll
      for (int i = 0; i < 4; i++) { d[i][0] = 0.f; d[i][1] = 0.f; d[i][2] = 0.f; d[i][3] = 0.f; }
#pragma unroll
      for (int ks = 0; ks < 8; ks++) {
        const uint2 hb = lds2(own + 256 + ks * 32 + tq * 8);
#pragma unroll
        for (int mt = 0; mt < 4; mt++) {
          const int r = ks * 16 + mt * 4;
          mma16816(d[mt], wf[r], wf[r + 1], wf[r + 2], wf[r + 3], hb.x, hb.y);
        }
      }
      sts2(own + (tq * 8 + g) * 8, __float_as_uint((tq & 2) ? ((tq & 1) ? d[1][2] : d[1][0]) : ((tq & 1) ? d[0][2] : d[0][0])),
           __float_as_uint((tq & 2) ? ((tq & 1) ? d[3][2] : d[3][0]) : ((tq & 1) ? d[2][2] : d[2][0])));
      bar_sync(1, 256);
      uint32_t ab[4];
      {
        float G = 0.f, U = 0.f;
        uint2 pv[8];
#pragma unroll
        for (int w8 = 0; w8 < 8; w8++) pv[w8] = lds2(base + ln * 8 + ((FT_G >> (w8 >> 1) * 4) & 15) * UNIT + (w8 & 1) * 8192);
#pragma unroll
        for (int w8 = 0; w8 < 8; w8 += 2) {
          G += __uint_as_float(pv[w8].x) + __uint_as_float(pv[w8 + 1].x);
          U += __uint_as_float(pv[w8].y) + __uint_as_float(pv[w8 + 1].y);
        }
        const float act = rbf(silu_f(rbf(G))) * rbf(U);
        const uint32_t pk = pack_bf(act, __shfl_down_sync(0xffffffffu, act, 1));
#pragma unroll
        for (int i = 0; i < 4; i++) ab[i] = __shfl_sync(0xffffffffu, pk, i * 8 + tq * 2);
      }
      if (!wdok) {
        mbar_wait(bar_box + (8 + (warp >> 1)) * 8, 0);
#pragma unroll
        for (int f = 0; f < 16; f++) LOAD_WD(f);
      }
      PROF(8, ct == PT, 34); STAMP(13);
#pragma unroll
      for (int mt = 0; mt < 8; mt++) {
        d[mt][0] = 0.f; d[mt][1] = 0.f; d[mt][2] = 0.f; d[mt][3] = 0.f;
        mma16816(d[mt], wd[mt * 8], wd[mt * 8 + 1], wd[mt * 8 + 2], wd[mt * 8 + 3], ab[0], ab[1]);
        mma16816(d[mt], wd[mt * 8 + 4], wd[mt * 8 + 5], wd[mt * 8 + 6], wd[mt * 8 + 7], ab[2], ab[3]);
      }
      uint32_t yw[4];
#pragma unroll
      for (int i = 0; i < 4; i++) yw[i] = (tq & 1) ? pack_bf(d[2 * i][2], d[2 * i + 1][2]) : pack_bf(d[2 * i][0], d[2 * i + 1][0]);
      if (tq < 2) st_b128(ydst, (yw[0] & ~1u) | (tag & 1), (yw[1] & ~1u) | (tag >> 1), yw[2], yw[3]);
      PROF(8, ct == PT, 35); STAMP(14);
    }
    mbar_wait(bar_sel, 0);
    mbar_arrive_pred(bar_win, ct == 0);
    const int iwin = lds1(par + PAR_CONST + 60) & 0x7ff;
    const bool cand = (iwin >> 4) == rb * 8 + warp;
    {
      const uint32_t mm0 = __shfl_sync(0xffffffffu, mm, ln & ~1), mm1 = __shfl_sync(0xffffffffu, mm, ln | 1);
      const uint32_t ih0 = __shfl_sync(0xffffffffu, ih, ln & ~1), ih1 = __shfl_sync(0xffffffffu, ih, ln | 1);
      const uint32_t il0 = __shfl_sync(0xffffffffu, il, ln & ~1), il1 = __shfl_sync(0xffffffffu, il, ln | 1);
#pragma unroll 1
      for (int hf = 0; hf < 2; hf++) {
        uint32_t x[16];
#pragma unroll
        for (int i = 0; i < 8; i += 2) ldmatrix4((trow ^ (i << 4)) + hf * 16384, x[2 * i], x[2 * i + 1], x[2 * i + 2], x[2 * i + 3]);
#pragma unroll
        for (int i = 0; i < 8; i++) {
          const uint4 pv = lds4(par + PAR_T2 + (hf * 8 + i) * 64 + tq * 16);
          x[2 * i] = hfma2(hfma2(ln_norm(x[2 * i], mm0, ih0, il0), pv.x, pv.y), pv.z, x[2 * i]);
          x[2 * i + 1] = hfma2(hfma2(ln_norm(x[2 * i + 1], mm1, ih1, il1), pv.x, pv.y), pv.z, x[2 * i + 1]);
        }
#pragma unroll
        for (int i = 0; i < 8; i += 2) stmatrix4((trow ^ (i << 4)) + hf * 16384, x[2 * i], x[2 * i + 1], x[2 * i + 2], x[2 * i + 3]);
        if (!cand) fence_async_smem();
        __syncwarp();
        if (!cand && elect_one()) {
          tma2d_store(&maps.out, res + hf * 16384 + warp * 2048, cj * 128 + hf * 64, rb * 128 + warp * 16);
          asm volatile("cp.async.bulk.commit_group;" ::: "memory");
        }
      }
    }
    if (cand) {
      const int wrow0 = warp * 16;
#pragma unroll 2
      for (int p = 0; p < 8; p++) {
        const int row = 2 * p + (ln >> 4), ch = ln & 15;
        const uint4 v = lds4(res + (ch >> 3) * 16384 + (wrow0 + row) * 128 + (((ch & 7) ^ (row & 7)) << 4));
        if (rb * 128 + wrow0 + row != iwin) *reinterpret_cast<uint4*>(P.out + (size_t)(rb * 128 + wrow0 + row) * DM + cj * 128 + ch * 8) = v;
      }
    }
    asm volatile("cp.async.bulk.wait_group.read 0;" ::: "memory");
    PROF(8, ct == PT, 11); STAMP(15);
    cluster_wait();
  }
}

typedef CUresult (*EncodeFn)(CUtensorMap*, CUtensorMapDataType, cuuint32_t, void*, const cuuint64_t*, const cuuint64_t*,
                             const cuuint32_t*, const cuuint32_t*, CUtensorMapInterleave, CUtensorMapSwizzle,
                             CUtensorMapL2promotion, CUtensorMapFloatOOBfill);

void map2d(EncodeFn enc, CUtensorMap* m, const void* p, uint64_t rows, uint64_t cols, uint32_t brows) {
  cuuint64_t dims[2] = {cols, rows}, strides[1] = {cols * 2};
  cuuint32_t box[2] = {64, brows}, es[2] = {1, 1};
  enc(m, CU_TENSOR_MAP_DATA_TYPE_BFLOAT16, 2, const_cast<void*>(p), dims, strides, box, es, CU_TENSOR_MAP_INTERLEAVE_NONE,
      CU_TENSOR_MAP_SWIZZLE_128B, CU_TENSOR_MAP_L2_PROMOTION_L2_256B, CU_TENSOR_MAP_FLOAT_OOB_FILL_NONE);
}
void map2d_narrow(EncodeFn enc, CUtensorMap* m, const void* p, uint64_t rows, uint64_t cols, uint32_t brows) {
  cuuint64_t dims[2] = {cols, rows}, strides[1] = {cols * 2};
  cuuint32_t box[2] = {32, brows}, es[2] = {1, 1};
  enc(m, CU_TENSOR_MAP_DATA_TYPE_BFLOAT16, 2, const_cast<void*>(p), dims, strides, box, es, CU_TENSOR_MAP_INTERLEAVE_NONE,
      CU_TENSOR_MAP_SWIZZLE_64B, CU_TENSOR_MAP_L2_PROMOTION_L2_64B, CU_TENSOR_MAP_FLOAT_OOB_FILL_NONE);
}
void map3d(EncodeFn enc, CUtensorMap* m, const void* p, uint64_t rows, uint64_t cols, uint32_t brows, uint32_t nch) {
  cuuint64_t dims[3] = {64, rows, cols / 64}, strides[2] = {cols * 2, 128};
  cuuint32_t box[3] = {64, brows, nch}, es[3] = {1, 1, 1};
  enc(m, CU_TENSOR_MAP_DATA_TYPE_BFLOAT16, 3, const_cast<void*>(p), dims, strides, box, es, CU_TENSOR_MAP_INTERLEAVE_NONE,
      CU_TENSOR_MAP_SWIZZLE_128B, CU_TENSOR_MAP_L2_PROMOTION_L2_256B, CU_TENSOR_MAP_FLOAT_OOB_FILL_NONE);
}

}

extern "C" void kernel_launch(void* const* d_in, const int* in_sizes, int n_in, void* d_out, int out_size) {
  (void)in_sizes; (void)n_in; (void)out_size;
  static EncodeFn enc = nullptr;
  if (!enc) {
    void* fn = nullptr;
    cudaDriverEntryPointQueryResult st;
    cudaGetDriverEntryPoint("cuTensorMapEncodeTiled", &fn, cudaEnableDefault, &st);
    enc = (EncodeFn)fn;
    cudaFuncSetAttribute(fused_kernel, cudaFuncAttributeMaxDynamicSharedMemorySize, SMEM_BYTES);
  }
  Maps maps;
  map2d(enc, &maps.x, d_in[0], SEQ, DM, 128);
  map2d(enc, &maps.out, d_out, SEQ, DM, 16);
  map3d(enc, &maps.wq, d_in[3], DM, NQ, 64, 2);
  map3d(enc, &maps.k, d_in[1], 4 * SK, 128, 128, 1);
  map3d(enc, &maps.v, d_in[2], 4 * SK, 128, 128, 1);
  map3d(enc, &maps.wo, d_in[4], NQ, DM, 64, 2);
  map2d_narrow(enc, &maps.wg, d_in[7], DM, FF, 256);
  map2d_narrow(enc, &maps.wu, d_in[8], DM, FF, 256);
  map3d(enc, &maps.wd, d_in[9], FF, DM, 32, 4);
  map2d_narrow(enc, &maps.wm, d_in[11], DM, NMOD, 256);
  Ptrs p;
  p.x = (const __nv_bfloat16*)d_in[0];
  p.w_r = (const __nv_bfloat16*)d_in[6];
  p.w_gate = (const __nv_bfloat16*)d_in[7];
  p.w_up = (const __nv_bfloat16*)d_in[8];
  p.w_down = (const __nv_bfloat16*)d_in[9];
  p.c = (const __nv_bfloat16*)d_in[10];
  p.w_mod = (const __nv_bfloat16*)d_in[11];
  p.out = (__nv_bfloat16*)d_out;
  fused_kernel<<<NMAIN + NHELP, 384, SMEM_BYTES>>>(maps, p);
}
```

```cpp
#include <cuda_runtime.h>
#include <cuda_bf16.h>
#include <cuda.h>
#include <stdint.h>
#include <type_traits>

#define HD 2
#define HDX 2
#define NRS 8
#define OSL 900
#define OSL2 400
#define RSL 40
#define BIAS 102.f
#define VREL 5
#define OPS 8192
#define ODS1 5
#define ODS 7
#define PG0 15
#define WB 2
#define WN 20
#define HU 32
#define RES0 17
#define RES1 20
#define GOST 20
#define NS1 5
#define LD2 4
#define FPACE0 2
#define FPACE 3
#define CR 8
#define CS 8

namespace {

constexpr int SEQ = 2048, DM = 1024, NQ = 4096, SK = 2048, WIN = 512, FF = 3584, NMOD = 6144;
constexpr int NMAIN = 128, NHELP = 4, NFFN = 112;
constexpr int NSLOT = 4, SLOT_BYTES = 32768, UNIT = 16384, GST_BYTES = 3 * UNIT;
constexpr uint32_t XT1 = 0xDCBA, XT2 = 0x9687;
constexpr uint32_t WT0 = 0xA741, WT1 = 0x7420, WT2 = 0x4A20;
constexpr uint32_t AT0 = WT1, AT1 = WT2;
constexpr uint32_t QT = 0xDC9696DC;
constexpr int OFF_STAGE = 12 * UNIT;
constexpr uint32_t FT_G = 0x07B3, FT_U = 0xA628, FT_D = 0x5149;
constexpr int OFF_RES = 12 * UNIT;
constexpr int OFF_PAR = 14 * UNIT;
constexpr int OFF_BAR = OFF_PAR + 2528;
constexpr int SMEM_BYTES = OFF_BAR + 544;
static_assert(SMEM_BYTES <= 232448, "smem");

constexpr int PAR_T1 = 0;
constexpr int PAR_T2 = 512;
constexpr int PAR_CONST = 1536;
constexpr int PAR_RED = 1600;
constexpr int PAR_SINK = 2176;

struct Maps {
  CUtensorMap x, wq, k, v, wo, wg, wu, wd, wm, out;
};
struct Ptrs {
  const __nv_bfloat16 *x, *c, *w_r, *w_mod, *w_gate, *w_up, *w_down;
  __nv_bfloat16* out;
};

__device__ __align__(1024) uint8_t g_act[16 * 80 * UNIT];
__device__ __align__(128) uint32_t g_mod[NMOD];
__device__ __align__(128) uint32_t g_modp[2 * 2 * DM];
__device__ __align__(128) uint32_t g_ln1[SEQ * 4];
__device__ __align__(128) uint32_t g_cnt_h[16 * 32];
__device__ __align__(128) uint32_t g_cnt_o[128 * 32];
__device__ __align__(128) uint32_t g_xch[NMAIN * 8 * 256 * 4];
__device__ __align__(128) uint32_t g_stats[8 * SEQ * 4];
__device__ __align__(128) uint32_t g_cand[CR * 512];
__device__ __align__(128) uint32_t g_row[16 * 2 * DM];
__device__ __align__(128) uint32_t g_ypart[NMAIN * NFFN * 4];
__device__ __forceinline__ uint32_t* ypart_slot(int writer, int reader) { return g_ypart + (writer * NMAIN + reader) * 4; }
__device__ uint32_t g_epoch;

__device__ __forceinline__ uint32_t fresh_lane() { uint32_t l; asm volatile("mov.u32 %0, %%laneid;" : "=r"(l)); return l; }
__device__ __forceinline__ uint32_t frag_offset(int warp) {
  const uint32_t l = fresh_lane();
  return ((warp & 3) * 16 + (l & 15)) * 128 + (((l >> 4) ^ (l & 7)) << 4);
}
__device__ __forceinline__ bool elect_one() {
  uint32_t p;
  asm volatile("{ .reg .pred q; elect.sync _|q, 0xffffffff; selp.u32 %0, 1, 0, q; }" : "=r"(p));
  return p;
}
__device__ __forceinline__ uint32_t smem_u32(const void* p) { return (uint32_t)__cvta_generic_to_shared(p); }
__device__ __forceinline__ void mbar_init(uint32_t bar, uint32_t cnt) {
  asm volatile("mbarrier.init.shared::cta.b64 [%0], %1;" ::"r"(bar), "r"(cnt) : "memory");
}
__device__ __forceinline__ void mbar_expect_tx(uint32_t bar, uint32_t bytes) {
  asm volatile("mbarrier.arrive.expect_tx.shared::cta.b64 _, [%0], %1;" ::"r"(bar), "r"(bytes) : "memory");
}
__device__ __forceinline__ void mbar_arrive(uint32_t bar) {
  asm volatile("mbarrier.arrive.shared::cta.b64 _, [%0];" ::"r"(bar) : "memory");
}
__device__ __forceinline__ void mbar_arrive_pred(uint32_t bar, bool p) {
  asm volatile("{ .reg .pred p; setp.ne.b32 p, %1, 0; @p mbarrier.arrive.shared::cta.b64 _, [%0]; }" ::"r"(bar), "r"((int)p) : "memory");
}
__device__ __forceinline__ void mbar_arrive_cl(uint32_t bar, uint32_t off, bool p = true) {
  asm volatile("{ .reg .pred p, q; .reg .b32 a; setp.ne.b32 q, %2, 0; setp.ne.and.b32 p, %0, 0, q; add.u32 a, %0, %1; @p mbarrier.arrive.shared::cluster.b64 _, [a]; }"
               ::"r"(bar), "r"(off), "r"((int)p) : "memory");
}
__device__ __forceinline__ uint32_t mapa(uint32_t addr, uint32_t cta) {
  uint32_t r; asm("mapa.shared::cluster.u32 %0, %1, %2;" : "=r"(r) : "r"(addr), "r"(cta)); return r;
}
__device__ __forceinline__ void cluster_arrive() { asm volatile("barrier.cluster.arrive.relaxed.aligned;" ::: "memory"); }
__device__ __forceinline__ void cluster_wait() { asm volatile("barrier.cluster.wait.aligned;" ::: "memory"); }
__device__ __forceinline__ void watchdog(uint32_t& n) {
}
__device__ __forceinline__ void mbar_wait(uint32_t bar, uint32_t parity) {
  asm volatile("{\n.reg .pred p;\nWAIT_%=:\nmbarrier.try_wait.parity.shared::cta.b64 p, [%0], %1;\n@!p bra WAIT_%=;\n}" ::"r"(bar), "r"(parity) : "memory");
}
__device__ __forceinline__ bool mbar_test(uint32_t bar, uint32_t parity) {
  uint32_t ok;
  asm volatile("{\n.reg .pred p;\nmbarrier.test_wait.parity.shared::cta.b64 p, [%1], %2;\nselp.u32 %0, 1, 0, p;\n}" : "=r"(ok) : "r"(bar), "r"(parity) : "memory");
  return ok;
}
__device__ __forceinline__ uint64_t l2_stream() {
  uint64_t f; asm("createpolicy.fractional.L2::evict_first.b64 %0, 1.0;" : "=l"(f)); return f;
}
__device__ __forceinline__ uint64_t l2_normal() {
  uint64_t f; asm("createpolicy.fractional.L2::evict_normal.b64 %0, 1.0;" : "=l"(f)); return f;
}
__device__ __forceinline__ void tma2d(uint32_t dst, const CUtensorMap* m, int c0, int c1, uint32_t bar) {
  asm volatile("cp.async.bulk.tensor.2d.shared::cluster.global.mbarrier::complete_tx::bytes.L2::cache_hint [%0], [%1, {%3, %4}], [%2], %5;"
               ::"r"(dst), "l"(m), "r"(bar), "r"(c0), "r"(c1), "l"(l2_stream()) : "memory");
}
__device__ __forceinline__ void bulk_load(uint32_t dst, const void* src, uint32_t bytes, uint32_t bar) {
  asm volatile("cp.async.bulk.shared::cluster.global.mbarrier::complete_tx::bytes [%0], [%1], %2, [%3];" ::"r"(dst), "l"(src), "r"(bytes), "r"(bar) : "memory");
}
__device__ __forceinline__ void bulk_load_stream(uint32_t dst, const void* src, uint32_t bytes, uint32_t bar, uint64_t pol = l2_stream()) {
  asm volatile("cp.async.bulk.shared::cluster.global.mbarrier::complete_tx::bytes.L2::cache_hint [%0], [%1], %2, [%3], %4;"
               ::"r"(dst), "l"(src), "r"(bytes), "r"(bar), "l"(pol) : "memory");
}
__device__ __forceinline__ void tma2d_store(const CUtensorMap* m, uint32_t src, int c0, int c1) {
  asm volatile("cp.async.bulk.tensor.2d.global.shared::cta.bulk_group [%0, {%2, %3}], [%1];" ::"l"(m), "r"(src), "r"(c0), "r"(c1) : "memory");
}
__device__ __forceinline__ void bulk_store(void* dst, uint32_t src, uint32_t bytes) {
  asm volatile("cp.async.bulk.global.shared::cta.bulk_group [%0], [%1], %2;" ::"l"(dst), "r"(src), "r"(bytes) : "memory");
}
__device__ __forceinline__ int slice_of(int i) { return (i & 8) + ((0x76531420u >> (i & 7) * 4) & 7); }
__device__ __forceinline__ uint32_t unit_of(uint32_t table, uint32_t i) { return ((table >> (i * 4)) & 15) * UNIT; }
__device__ __forceinline__ void tma3d(uint32_t dst, const CUtensorMap* m, int c0, int c1, int c2, uint32_t bar) {
  asm volatile("cp.async.bulk.tensor.3d.shared::cluster.global.mbarrier::complete_tx::bytes.L2::cache_hint [%0], [%1, {%3, %4, %5}], [%2], %6;"
               ::"r"(dst), "l"(m), "r"(bar), "r"(c0), "r"(c1), "r"(c2), "l"(l2_stream()) : "memory");
}
template <bool STREAM>
__device__ __forceinline__ void tma3d_mc(uint32_t dst, const CUtensorMap* m, int c0, int c1, int c2, uint32_t bar) {
  if (STREAM)
    asm volatile("cp.async.bulk.tensor.3d.shared::cluster.global.mbarrier::complete_tx::bytes.multicast::cluster.L2::cache_hint [%0], [%1, {%3, %4, %5}], [%2], %6, %7;"
                 ::"r"(dst), "l"(m), "r"(bar), "r"(c0), "r"(c1), "r"(c2), "h"((uint16_t)3), "l"(l2_stream()) : "memory");
  else
    asm volatile("cp.async.bulk.tensor.3d.shared::cluster.global.mbarrier::complete_tx::bytes.multicast::cluster [%0], [%1, {%3, %4, %5}], [%2], %6;"
                 ::"r"(dst), "l"(m), "r"(bar), "r"(c0), "r"(c1), "r"(c2), "h"((uint16_t)3) : "memory");
}
__device__ __forceinline__ void prefetch_map(const CUtensorMap* m) {
  asm volatile("prefetch.tensormap [%0];" ::"l"(m) : "memory");
}
__device__ __forceinline__ void fence_async() { asm volatile("fence.proxy.async.global;" ::: "memory"); }
__device__ __forceinline__ void fence_async_smem() { asm volatile("fence.proxy.async.shared::cta;" ::: "memory"); }
__device__ __forceinline__ void bar_sync(int id, int n) { asm volatile("bar.sync %0, %1;" ::"r"(id), "r"(n) : "memory"); }
__device__ __forceinline__ void bar_arrive(int id, int n) { asm volatile("bar.arrive %0, %1;" ::"r"(id), "r"(n) : "memory"); }
__device__ __forceinline__ void wg_fence() { asm volatile("wgmma.fence.sync.aligned;" ::: "memory"); }
__device__ __forceinline__ void wg_commit() { asm volatile("wgmma.commit_group.sync.aligned;" ::: "memory"); }
template <int N> __device__ __forceinline__ void wg_wait() { asm volatile("wgmma.wait_group.sync.aligned %0;" ::"n"(N) : "memory"); }
__device__ __forceinline__ uint64_t make_desc(uint32_t addr, uint32_t lbo, uint32_t sbo) {
  return (uint64_t)((addr & 0x3FFFF) >> 4) | ((uint64_t)(lbo >> 4) << 16) | ((uint64_t)(sbo >> 4) << 32) | (1ull << 62);
}
__device__ __forceinline__ uint32_t ld_relaxed(const uint32_t* p) {
  uint32_t v; asm volatile("ld.relaxed.gpu.global.u32 %0, [%1];" : "=r"(v) : "l"(p) : "memory"); return v;
}
__device__ __forceinline__ uint32_t ld_acquire(const uint32_t* p) {
  uint32_t v; asm volatile("ld.acquire.gpu.global.u32 %0, [%1];" : "=r"(v) : "l"(p) : "memory"); return v;
}
__device__ __forceinline__ uint4 ld_relaxed4(const uint32_t* p) {
  uint4 v; asm volatile("ld.relaxed.gpu.global.v4.u32 {%0,%1,%2,%3}, [%4];" : "=r"(v.x), "=r"(v.y), "=r"(v.z), "=r"(v.w) : "l"(p) : "memory"); return v;
}
__device__ __forceinline__ void st_relaxed(uint32_t* p, uint32_t v) {
  asm volatile("st.relaxed.gpu.global.u32 [%0], %1;" ::"l"(p), "r"(v) : "memory");
}
__device__ __forceinline__ void st_relaxed4(uint32_t* p, uint32_t a, uint32_t b, uint32_t c, uint32_t d) {
  asm volatile("st.relaxed.gpu.global.v4.u32 [%0], {%1,%2,%3,%4};" ::"l"(p), "r"(a), "r"(b), "r"(c), "r"(d) : "memory");
}
__device__ __forceinline__ void st_b128(uint32_t* p, uint32_t a, uint32_t b, uint32_t c, uint32_t d) {
  asm volatile("{ .reg .b64 u, v; .reg .b128 w; mov.b64 u, {%1, %2}; mov.b64 v, {%3, %4}; mov.b128 w, {u, v}; st.relaxed.gpu.global.b128 [%0], w; }"
               ::"l"(p), "r"(a), "r"(b), "r"(c), "r"(d) : "memory");
}
__device__ __forceinline__ uint4 ld_b128(const uint32_t* p) {
  uint4 r;
  asm volatile("{ .reg .b64 u, v; .reg .b128 w; ld.relaxed.gpu.global.b128 w, [%4]; mov.b128 {u, v}, w; mov.b64 {%0, %1}, u; mov.b64 {%2, %3}, v; }"
               : "=r"(r.x), "=r"(r.y), "=r"(r.z), "=r"(r.w) : "l"(p) : "memory");
  return r;
}
__device__ __forceinline__ void st_pairs(uint32_t* p, uint32_t a, uint32_t b, uint32_t tag) {
  asm volatile("{ .reg .b64 u, v; mov.b64 u, {%1, %3}; mov.b64 v, {%2, %3}; st.relaxed.gpu.global.v2.b64 [%0], {u, v}; }"
               ::"l"(p), "r"(a), "r"(b), "r"(tag) : "memory");
}
__device__ __forceinline__ uint4 ld_pairs(const uint32_t* p) {
  uint4 v;
  asm volatile("{ .reg .b64 u, v; ld.relaxed.gpu.global.v2.b64 {u, v}, [%4]; mov.b64 {%0, %1}, u; mov.b64 {%2, %3}, v; }"
               : "=r"(v.x), "=r"(v.y), "=r"(v.z), "=r"(v.w) : "l"(p) : "memory");
  return v;
}
__device__ __forceinline__ uint2 ld_pair(const uint32_t* p) {
  uint2 v;
  asm volatile("{ .reg .b64 u; ld.relaxed.gpu.global.b64 u, [%2]; mov.b64 {%0, %1}, u; }" : "=r"(v.x), "=r"(v.y) : "l"(p) : "memory");
  return v;
}
__device__ __forceinline__ void red_release(uint32_t* p, uint32_t v) {
  asm volatile("red.release.gpu.global.add.u32 [%0], %1;" ::"l"(p), "r"(v) : "memory");
}
__device__ __forceinline__ uint32_t ldg_nc1(const void* p) {
  uint32_t v;
  asm volatile("ld.global.nc.u32 %0, [%1];" : "=r"(v) : "l"(p));
  return v;
}
__device__ __forceinline__ uint4 ldg_nc4(const void* p) {
  uint4 v; asm volatile("ld.global.nc.L1::no_allocate.v4.u32 {%0,%1,%2,%3}, [%4];" : "=r"(v.x), "=r"(v.y), "=r"(v.z), "=r"(v.w) : "l"(p)); return v;
}
__device__ __forceinline__ uint4 ldg_stream4(const void* p) {
  uint4 v;
  asm volatile("ld.global.nc.L1::no_allocate.L2::cache_hint.v4.u32 {%0,%1,%2,%3}, [%4], %5;" : "=r"(v.x), "=r"(v.y), "=r"(v.z), "=r"(v.w) : "l"(p), "l"(l2_stream()));
  return v;
}
__device__ __forceinline__ void stg4(void* p, uint4 v) {
  asm volatile("st.global.v4.u32 [%0], {%1,%2,%3,%4};" ::"l"(p), "r"(v.x), "r"(v.y), "r"(v.z), "r"(v.w) : "memory");
}
__device__ __forceinline__ void wait_counter(const uint32_t* p, uint32_t target) {
  uint32_t n = 0;
  while (__any_sync(0xffffffffu, (int)(ld_acquire(p) - target) < 0)) { watchdog(n); }
}
__device__ __forceinline__ uint32_t tagf(float v, uint32_t tag) { return (__float_as_uint(v) & ~3u) | tag; }
__device__ __forceinline__ bool tag_ok(uint4 v, uint32_t tag) { return (((v.x ^ tag) | (v.y ^ tag) | (v.z ^ tag) | (v.w ^ tag)) & 3u) == 0; }
__device__ __forceinline__ float untag_sum(uint32_t a, uint32_t b) { return __uint_as_float(a & ~3u) + __uint_as_float(b & ~3u); }
__device__ __forceinline__ uint4 poll4(const uint32_t* p, uint32_t tag) {
  uint4 v = ld_relaxed4(p);
  uint32_t n = 0;
  while (!__all_sync(0xffffffffu, tag_ok(v, tag))) { v = ld_relaxed4(p); watchdog(n); }
  return v;
}
__device__ __forceinline__ float bf_lo(uint32_t v) { return __uint_as_float(v << 16); }
__device__ __forceinline__ float bf_hi(uint32_t v) { return __uint_as_float(v & 0xffff0000u); }
__device__ __forceinline__ uint32_t pack_bf(float lo, float hi) {
  uint32_t r; asm("cvt.rn.bf16x2.f32 %0, %1, %2;" : "=r"(r) : "f"(hi), "f"(lo)); return r;
}
__device__ __forceinline__ float rbf(float v) { return __uint_as_float(pack_bf(0.f, v) & 0xffff0000u); }
__device__ __forceinline__ uint32_t hmul2(uint32_t a, uint32_t b) {
  uint32_t r; asm("mul.rn.bf16x2 %0, %1, %2;" : "=r"(r) : "r"(a), "r"(b)); return r;
}
__device__ __forceinline__ uint32_t hadd2(uint32_t a, uint32_t b) {
  uint32_t r; asm("add.rn.bf16x2 %0, %1, %2;" : "=r"(r) : "r"(a), "r"(b)); return r;
}
__device__ __forceinline__ uint32_t hsub2(uint32_t a, uint32_t b) {
  uint32_t r; asm("sub.rn.bf16x2 %0, %1, %2;" : "=r"(r) : "r"(a), "r"(b)); return r;
}
__device__ __forceinline__ float rcp(float x) { float r; asm("rcp.approx.ftz.f32 %0, %1;" : "=f"(r) : "f"(x)); return r; }
__device__ __forceinline__ float ex2(float x) { float r; asm("ex2.approx.ftz.f32 %0, %1;" : "=f"(r) : "f"(x)); return r; }
__device__ __forceinline__ void stmatrix4(uint32_t addr, uint32_t a, uint32_t b, uint32_t c, uint32_t d) {
  asm volatile("stmatrix.sync.aligned.m8n8.x4.shared.b16 [%0], {%1,%2,%3,%4};" ::"r"(addr), "r"(a), "r"(b), "r"(c), "r"(d) : "memory");
}
__device__ __forceinline__ void ldmatrix4(uint32_t addr, uint32_t& a, uint32_t& b, uint32_t& c, uint32_t& d) {
  asm volatile("ldmatrix.sync.aligned.m8n8.x4.shared.b16 {%0,%1,%2,%3}, [%4];" : "=r"(a), "=r"(b), "=r"(c), "=r"(d) : "r"(addr) : "memory");
}
__device__ __forceinline__ void ldmatrix4t(uint32_t addr, uint32_t& a, uint32_t& b, uint32_t& c, uint32_t& d) {
  asm volatile("ldmatrix.sync.aligned.m8n8.x4.trans.shared.b16 {%0,%1,%2,%3}, [%4];" : "=r"(a), "=r"(b), "=r"(c), "=r"(d) : "r"(addr) : "memory");
}
__device__ __forceinline__ void mma16816(float (&d)[4], uint32_t a0, uint32_t a1, uint32_t a2, uint32_t a3, uint32_t b0, uint32_t b1) {
  asm volatile("mma.sync.aligned.m16n8k16.row.col.f32.bf16.bf16.f32 {%0,%1,%2,%3}, {%4,%5,%6,%7}, {%8,%9}, {%0,%1,%2,%3};"
               : "+f"(d[0]), "+f"(d[1]), "+f"(d[2]), "+f"(d[3]) : "r"(a0), "r"(a1), "r"(a2), "r"(a3), "r"(b0), "r"(b1));
}
__device__ __forceinline__ void sts1(uint32_t a, uint32_t v) { asm volatile("st.shared.u32 [%0], %1;" ::"r"(a), "r"(v) : "memory"); }
__device__ __forceinline__ uint4 lds4(uint32_t a) {
  uint4 v; asm volatile("ld.shared.v4.u32 {%0,%1,%2,%3}, [%4];" : "=r"(v.x), "=r"(v.y), "=r"(v.z), "=r"(v.w) : "r"(a) : "memory"); return v;
}
__device__ __forceinline__ uint2 lds2(uint32_t a) {
  uint2 v; asm volatile("ld.shared.v2.u32 {%0,%1}, [%2];" : "=r"(v.x), "=r"(v.y) : "r"(a) : "memory"); return v;
}
__device__ __forceinline__ uint32_t lds1(uint32_t a) {
  uint32_t v; asm volatile("ld.shared.u32 %0, [%1];" : "=r"(v) : "r"(a) : "memory"); return v;
}
__device__ __forceinline__ void sts2(uint32_t a, uint32_t x, uint32_t y) { asm volatile("st.shared.v2.u32 [%0], {%1,%2};" ::"r"(a), "r"(x), "r"(y) : "memory"); }
__device__ __forceinline__ void sts4(uint32_t a, uint4 v) {
  asm volatile("st.shared.v4.u32 [%0], {%1,%2,%3,%4};" ::"r"(a), "r"(v.x), "r"(v.y), "r"(v.z), "r"(v.w) : "memory");
}
__device__ __forceinline__ float silu_f(float v) { return __fdividef(v, 1.f + __expf(-v)); }
__device__ __forceinline__ uint32_t hfma2(uint32_t a, uint32_t b, uint32_t c) {
  uint32_t r; asm("fma.rn.bf16x2 %0, %1, %2, %3;" : "=r"(r) : "r"(a), "r"(b), "r"(c)); return r;
}
__device__ __forceinline__ void split_inv(float sd, uint32_t& ih, uint32_t& il) {
  const float inv = rcp(sd);
  ih = pack_bf(inv, inv);
  const float lo = inv - bf_lo(ih);
  il = pack_bf(lo, lo);
}
__device__ __forceinline__ uint32_t ln_norm(uint32_t x, uint32_t mean2, uint32_t ih, uint32_t il) {
  const uint32_t d = hsub2(x, mean2);
  return hfma2(d, ih, hmul2(d, il));
}
__device__ __forceinline__ uint32_t ln_mod(uint32_t x, uint32_t mean2, uint32_t ih, uint32_t il, uint32_t c1, uint32_t sh) {
  return hadd2(hmul2(ln_norm(x, mean2, ih, il), c1), sh);
}

#define R8(a, i) "+f"(a[i]), "+f"(a[i + 1]), "+f"(a[i + 2]), "+f"(a[i + 3]), "+f"(a[i + 4]), "+f"(a[i + 5]), "+f"(a[i + 6]), "+f"(a[i + 7])
#define D64 "{%0,%1,%2,%3,%4,%5,%6,%7,%8,%9,%10,%11,%12,%13,%14,%15,%16,%17,%18,%19,%20,%21,%22,%23,%24,%25,%26,%27,%28,%29,%30,%31," \
            "%32,%33,%34,%35,%36,%37,%38,%39,%40,%41,%42,%43,%44,%45,%46,%47,%48,%49,%50,%51,%52,%53,%54,%55,%56,%57,%58,%59,%60,%61,%62,%63}"
template <int TB>
__device__ __forceinline__ void mma_ss(float (&d)[64], uint64_t da, uint64_t db, int sc) {
  asm volatile("{\n.reg .pred p;\nsetp.ne.b32 p, %66, 0;\n"
               "wgmma.mma_async.sync.aligned.m64n128k16.f32.bf16.bf16 " D64 ", %64, %65, p, 1, 1, 0, %67;\n}"
               : R8(d, 0), R8(d, 8), R8(d, 16), R8(d, 24), R8(d, 32), R8(d, 40), R8(d, 48), R8(d, 56)
               : "l"(da), "l"(db), "r"(sc), "n"(TB));
}
template <int TB>
__device__ __forceinline__ void mma_rs(float (&d)[64], uint32_t a0, uint32_t a1, uint32_t a2, uint32_t a3, uint64_t db, int sc) {
  asm volatile("{\n.reg .pred p;\nsetp.ne.b32 p, %69, 0;\n"
               "wgmma.mma_async.sync.aligned.m64n128k16.f32.bf16.bf16 " D64 ", {%64,%65,%66,%67}, %68, p, 1, 1, %70;\n}"
               : R8(d, 0), R8(d, 8), R8(d, 16), R8(d, 24), R8(d, 32), R8(d, 40), R8(d, 48), R8(d, 56)
               : "r"(a0), "r"(a1), "r"(a2), "r"(a3), "l"(db), "r"(sc), "n"(TB));
}
#define D128 "{%0,%1,%2,%3,%4,%5,%6,%7,%8,%9,%10,%11,%12,%13,%14,%15,%16,%17,%18,%19,%20,%21,%22,%23,%24,%25,%26,%27,%28,%29,%30,%31," \
             "%32,%33,%34,%35,%36,%37,%38,%39,%40,%41,%42,%43,%44,%45,%46,%47,%48,%49,%50,%51,%52,%53,%54,%55,%56,%57,%58,%59,%60,%61,%62,%63," \
             "%64,%65,%66,%67,%68,%69,%70,%71,%72,%73,%74,%75,%76,%77,%78,%79,%80,%81,%82,%83,%84,%85,%86,%87,%88,%89,%90,%91,%92,%93,%94,%95," \
             "%96,%97,%98,%99,%100,%101,%102,%103,%104,%105,%106,%107,%108,%109,%110,%111,%112,%113,%114,%115,%116,%117,%118,%119,%120,%121,%122,%123,%124,%125,%126,%127}"
#define R128(d, e) R8(d, 0), R8(d, 8), R8(d, 16), R8(d, 24), R8(d, 32), R8(d, 40), R8(d, 48), R8(d, 56), \
                   R8(e, 0), R8(e, 8), R8(e, 16), R8(e, 24), R8(e, 32), R8(e, 40), R8(e, 48), R8(e, 56)
__device__ __forceinline__ void mma256_ss(float (&d)[64], float (&e)[64], uint64_t da, uint64_t db, int sc) {
  asm volatile("{\n.reg .pred p;\nsetp.ne.b32 p, %130, 0;\n"
               "wgmma.mma_async.sync.aligned.m64n256k16.f32.bf16.bf16 " D128 ", %128, %129, p, 1, 1, 0, 1;\n}"
               : R128(d, e) : "l"(da), "l"(db), "r"(sc));
}
__device__ __forceinline__ void mma256_rs(float (&d)[64], float (&e)[64], uint32_t a0, uint32_t a1, uint32_t a2, uint32_t a3, uint64_t db) {
  asm volatile("{\n.reg .pred p;\nsetp.ne.b32 p, 1, 0;\n"
               "wgmma.mma_async.sync.aligned.m64n256k16.f32.bf16.bf16 " D128 ", {%128,%129,%130,%131}, %132, p, 1, 1, 1;\n}"
               : R128(d, e) : "r"(a0), "r"(a1), "r"(a2), "r"(a3), "l"(db));
}
template <int N> __device__ __forceinline__ void keep(float (&a)[N]) {
#pragma unroll
  for (int i = 0; i < N; i++) asm volatile("" : "+f"(a[i])::"memory");
}
template <int N> __device__ __forceinline__ void keep(uint32_t (&a)[N]) {
#pragma unroll
  for (int i = 0; i < N; i++) asm volatile("" : "+r"(a[i])::"memory");
}

#define STAMP(idx) do {} while (0)
#define PROF(grp, cond, idx) do {} while (0)

constexpr float SCL2 = 1.4426950408889634f * 0.08838834764831845f;

__device__ __forceinline__ void pack_p(const float (&s)[64], uint32_t (&p)[32]) {
#pragma unroll
  for (int i = 0; i < 32; i++) p[i] = pack_bf(s[2 * i], s[2 * i + 1]);
}

__device__ __forceinline__ void issue_qk(float (&s)[64], uint32_t q0, uint32_t q1, uint32_t kslot) {
  const uint64_t db = make_desc(kslot, 16, 1024), da0 = make_desc(q0, 16, 1024), da1 = make_desc(q1, 16, 1024);
#pragma unroll
  for (int kk = 0; kk < 8; kk++) mma_ss<0>(s, (kk < 4 ? da0 : da1) + (kk & 3) * 2, db + (kk >> 2) * 1024 + (kk & 3) * 2, kk != 0);
}
__device__ __forceinline__ void issue_pv(float (&o)[64], uint32_t (&p)[32], uint32_t vslot, int acc) {
  uint64_t db = make_desc(vslot, 16384, 1024);
#pragma unroll
  for (int kk = 0; kk < 8; kk++)
    mma_rs<1>(o, p[4 * kk], p[4 * kk + 1], p[4 * kk + 2], p[4 * kk + 3], db + kk * 128, kk == 0 ? acc : 1);
}

template <int H>
__device__ __forceinline__ void store_chunk(const float (&a)[64], uint32_t addr) {
#pragma unroll
  for (int i = 8 * H; i < 8 * H + 8; i += 2)
    stmatrix4(addr ^ ((i & 7) << 4), pack_bf(a[4 * i], a[4 * i + 1]), pack_bf(a[4 * i + 2], a[4 * i + 3]),
              pack_bf(a[4 * i + 4], a[4 * i + 5]), pack_bf(a[4 * i + 6], a[4 * i + 7]));
}
template <int H>
__device__ __forceinline__ void store_chunk(const float (&a)[64], float i0, float i1, uint32_t addr) {
#pragma unroll
  for (int i = 8 * H; i < 8 * H + 8; i += 2)
    stmatrix4(addr ^ ((i & 7) << 4), pack_bf(a[4 * i] * i0, a[4 * i + 1] * i0), pack_bf(a[4 * i + 2] * i1, a[4 * i + 3] * i1),
              pack_bf(a[4 * i + 4] * i0, a[4 * i + 5] * i0), pack_bf(a[4 * i + 6] * i1, a[4 * i + 7] * i1));
}
__device__ __forceinline__ float inv_quad_sum(float l) {
  l += __shfl_xor_sync(0xffffffffu, l, 1);
  l += __shfl_xor_sync(0xffffffffu, l, 2);
  return rcp(l);
}

__device__ __forceinline__ void write_table(uint32_t table, bool ca, uint32_t t, const uint4& m0, const uint4& m1) {
  float c0 = untag_sum(m0.x, m1.x), c1 = untag_sum(m0.y, m1.y), c2 = untag_sum(m0.z, m1.z), c3 = untag_sum(m0.w, m1.w);
  if (ca) { c0 = 1.f + rbf(c0); c1 = 1.f + rbf(c1); c2 = 1.f + rbf(c2); c3 = 1.f + rbf(c3); }
  const uint32_t d = table + (t >> 2) * 64 + (t & 1) * 32 + (t & 2) * 2 + (ca ? 0 : 8);
  sts1(d, pack_bf(c0, c1));
  sts1(d + 16, pack_bf(c2, c3));
}

__device__ __forceinline__ void ln_scalars(float mean, float var, float& mb, float& sd) {
  mb = rbf(mean);
  float r; asm("sqrt.approx.ftz.f32 %0, %1;" : "=f"(r) : "f"(rbf(rbf(var) + 1e-5f)));
  sd = rbf(r);
}

__global__ void __cluster_dims__(2, 1, 1) __launch_bounds__(384, 1) fused_kernel(const Ptrs P, const __grid_constant__ Maps maps) {
  extern __shared__ __align__(1024) uint8_t smem_raw[];
  const uint32_t base = smem_u32(smem_raw);
  const int tid = threadIdx.x, lane = tid & 31;
  const int warp = __shfl_sync(0xffffffffu, tid >> 5, 0);
  int b = blockIdx.x;
  {
    const uint32_t p = b >> 1, q = (p - 36) * 37 >> 8, r = p - 36 - 7 * q;
    const uint32_t w = p < 4 ? 60 + p : (p < 36 ? ((p + 2) & 7) * 8 + ((p - 4) >> 3) : (r ? r - 1 : 6) * 8 + 4 + q);
    b = p < 64 ? w * 2 + (b & 1) : b;
  }
  PROF(31, tid == 0, 0);

  if (b >= NMAIN) {
    float* sc = reinterpret_cast<float*>(smem_raw);
    float* red = sc + DM;
    for (int k = tid; k < DM; k += 384) sc[k] = rbf(silu_f(__bfloat162float(P.c[k])));
    __syncthreads();
    if (tid < 256) {
      const int col = 2048 + (b - NMAIN) * 1024 + (tid & 127) * 8, r0 = (tid >> 7) * 512;
      float acc[8];
#pragma unroll
      for (int e = 0; e < 8; e++) acc[e] = 0.f;
#pragma unroll 1
      for (int r = r0; r < r0 + 512; r += HU) {
        uint4 w[HU];
#pragma unroll
        for (int u = 0; u < HU; u++) w[u] = ldg_stream4(P.w_mod + (size_t)(r + u) * NMOD + col);
#pragma unroll
        for (int u = 0; u < HU; u++) {
          float s = sc[r + u];
          acc[0] += s * bf_lo(w[u].x); acc[1] += s * bf_hi(w[u].x); acc[2] += s * bf_lo(w[u].y); acc[3] += s * bf_hi(w[u].y);
          acc[4] += s * bf_lo(w[u].z); acc[5] += s * bf_hi(w[u].z); acc[6] += s * bf_lo(w[u].w); acc[7] += s * bf_hi(w[u].w);
        }
      }
      if (tid >= 128) {
#pragma unroll
        for (int e = 0; e < 8; e++) red[(tid & 127) * 8 + e] = acc[e];
      }
      const uint32_t tag = ld_relaxed(&g_epoch) % 3 + 1;
      bar_sync(1, 256);
      if (tid < 128) {
        uint32_t o[8];
#pragma unroll
        for (int e = 0; e < 8; e++) o[e] = __float_as_uint(rbf(acc[e] + red[tid * 8 + e])) | tag;
        st_relaxed4(g_mod + col, o[0], o[1], o[2], o[3]);
        st_relaxed4(g_mod + col + 4, o[4], o[5], o[6], o[7]);
        const uint4 wr = ldg_nc4(P.w_r + tid * 8);
        const uint32_t wv[4] = {wr.x, wr.y, wr.z, wr.w};
        float dsum = 0.f;
#pragma unroll
        for (int e = 0; e < 8; e++) {
          const float m = bf_hi(o[e]);
          dsum += (b == NMAIN + 2 ? rbf(1.f + m) : m) * ((e & 1) ? bf_hi(wv[e >> 1]) : bf_lo(wv[e >> 1]));
        }
#pragma unroll
        for (int k = 16; k > 0; k >>= 1) dsum += __shfl_xor_sync(0xffffffffu, dsum, k);
        if (lane == 0) st_relaxed(g_mod + (b - NMAIN) * 4 + warp, tagf(dsum, tag));
      }
    }
    PROF(2, tid == 0, 1);
    return;
  }

  const int rank = b & 1;
  const int rb = ((b >> 4) << 1) | rank, cj = (b >> 1) & 7;
  const bool late = b & 4;
  const uint32_t bfull = base + OFF_BAR, bempty = bfull + NSLOT * 8;
  const uint32_t gfull = bempty + NSLOT * 8, gempty = gfull + 32;
  const uint32_t bar_ofull = gempty + 32;
  const uint32_t bar_ofree = bar_ofull + 32;
  const uint32_t bar_par = bar_ofree + 32;
  const uint32_t bar_mod = bar_par + 8;
  const uint32_t bar_pread = bar_mod + 8;
  const uint32_t bar_xres = bar_pread + 8;
  const uint32_t bar_ring = bar_xres + 8;
  const uint32_t bar_box = bar_ring + 24;
  const uint32_t bar_go = bar_box + 96;
  const uint32_t bar_go2 = bar_go + 16;
  const uint32_t bar_cnt = bar_go + 24;
  const uint32_t xfull = bar_go + 40, xempty = xfull + 32;
  const uint32_t bar_hw = xempty + 32, bar_hx = bar_hw + 8;
  const uint32_t bar_hpub = bar_hx + 16;
  const uint32_t bar_win = bar_hpub + 16;
  const uint32_t bar_rx = bar_win + 8;
  const uint32_t bar_sel = bar_rx + 8;
  const uint32_t bar_gate = bar_sel + 8;
  const uint32_t bar_rel = bar_gate + 8;
  const uint32_t bar_od = bar_rel + 8;
  const uint32_t bar_mod2 = bar_od + 8;
  const uint32_t bar_res = bar_go + 8;
  const uint32_t stage = base + OFF_STAGE, par = base + OFF_PAR;

  if (warp == 9 && elect_one()) {
    mbar_init(bar_hw, 1); mbar_init(bar_hx, 1); mbar_init(bar_hx + 8, 1);
    asm volatile("fence.mbarrier_init.release.cluster;" ::: "memory");
    mbar_expect_tx(bar_hw, 32768);
    mbar_expect_tx(bar_hx, 16384);
    mbar_expect_tx(bar_hx + 8, 16384);
    const __nv_bfloat16* xs = P.x + (size_t)(rb * 128 + cj * 16) * DM;
    bulk_load(base + 2 * GST_BYTES, xs, 16384, bar_hx);
    if (!late) {
      tma2d(stage, &maps.wm, (b >> 1) * 32, rank * 512, bar_hw);
      tma2d(stage + 16384, &maps.wm, (b >> 1) * 32, rank * 512 + 256, bar_hw);
    }
    bulk_load(base + 3 * GST_BYTES, xs + 8 * DM, 16384, bar_hx + 8);
  }
  if (warp == 10 && elect_one()) prefetch_map(&maps.wm);
  if (warp == 8 && elect_one()) {
    for (int s = 0; s < NSLOT; s++) { mbar_init(bfull + s * 8, 1); mbar_init(bempty + s * 8, 16); }
    for (int s = 0; s < 4; s++) { mbar_init(gfull + s * 8, 1); mbar_init(gempty + s * 8, 16); mbar_init(xfull + s * 8, 1); mbar_init(xempty + s * 8, 8); mbar_init(bar_ofree + s * 8, 1); mbar_init(bar_ofull + s * 8, 128); }
    mbar_init(bar_par, 64); mbar_init(bar_mod, 256); mbar_init(bar_pread, 2); mbar_init(bar_xres, 1);
    mbar_init(bar_ring, 8); mbar_init(bar_ring + 8, 8); mbar_init(bar_ring + 16, 8);
    mbar_init(bar_go, 1); mbar_init(bar_go2, 1); mbar_init(bar_cnt, 1); mbar_init(bar_cnt + 8, 1); mbar_init(bar_hpub, 8); mbar_init(bar_hpub + 8, 8); mbar_init(bar_res, 1); mbar_init(bar_win, 1); mbar_init(bar_rx, 1); mbar_init(bar_sel, 64); mbar_init(bar_gate, 8); mbar_init(bar_rel, 8); mbar_init(bar_od, 1); mbar_init(bar_mod2, 64);
    for (int s = 0; s < 12; s++) mbar_init(bar_box + s * 8, 1);
    asm volatile("fence.mbarrier_init.release.cluster;" ::: "memory");
    prefetch_map(&maps.x); prefetch_map(&maps.wq); prefetch_map(&maps.k); prefetch_map(&maps.v);
  }
  cluster_arrive();

  if (warp >= 8) {
    asm volatile("setmaxnreg.dec.sync.aligned.u32 40;");
    if (warp < 10) bar_arrive(1, 320);
    const uint32_t epoch = ld_relaxed(&g_epoch);
    cluster_wait();
    if (warp == 8) {
      const int kvrow = (cj >> 1) * SK + (SK - WIN);
      int wch = cj * 8 + rank * 2;
#pragma unroll 1
      for (int ps = 0; ps < 3; ps++) {
        const CUtensorMap* mw = ps == 2 ? &maps.wo : &maps.wq;
        const uint32_t xt = ps == 1 ? XT1 : XT2, wt = ps == 0 ? WT0 : (ps == 1 ? WT1 : WT2);
        const int nst = ps == 2 ? 32 : 16;
#pragma unroll 1
        for (int i = 0; i < nst; i++) {
          const uint32_t bf = gfull + (i & 3) * 8;
          const int kt = ps == 2 ? (((cj & 1) * 4 + ((i >> 1) & 3)) * 4 + (i >> 3)) * 2 + (i & 1) : (ps ? i : slice_of(i) + (b & 14)) & 15;
          const uint32_t wd = base + unit_of(wt, i & 3) + rank * UNIT, xd = base + unit_of(xt, i & 3);
          const uint8_t* xs = g_act + (uint32_t)(rb * 80 + (ps - 1) * 16 + kt) * UNIT;
          if (ps == 0 && i == HD) mbar_wait(bar_mod, 0);
          if (ps == 2 && (i & 7) == 0 && i != 8) mbar_wait(i ? bar_cnt + i - 16 : bar_ofree + 24, 0);
          if ((i & 7) == 0) fence_async();
          if (i == RES0) mbar_wait(bar_res, 0);
          mbar_wait(bf, ((i >> 2) & 1) ^ 1);
          if (elect_one()) {
            mbar_expect_tx(bf, ps ? GST_BYTES : 2 * UNIT);
            if (ps && i < 2) bulk_load_stream(xd, xs, UNIT, bf);
            mbar_arrive_pred(bar_go, i == GOST);
            mbar_arrive_pred(bar_go2, ps == 1 && i == PG0);
            mbar_arrive_pred(bar_od, ps && i == (ps == 1 ? ODS1 : ODS) + 1);
            if (i == RES0) mbar_expect_tx(bar_xres, 32768);
          }
          const int wk = (i == 31 ? kt ^ (rank * 32) : kt) * 64, wc = i == 31 ? cj * 2 : wch;
          const uint64_t xp = i == 31 ? l2_normal() : l2_stream();
          mbar_wait(ps && i < 4 ? bempty + i * 8 : gempty + (i & 3) * 8, ((i >> 2) & 1) ^ 1);
          if (elect_one()) {
            tma3d_mc<true>(wd, mw, 0, wk, wc, bf);
            if (ps && i > 2) bulk_load_stream(xd, xs, UNIT, bf, xp);
            if (i == RES0 || i == RES1) tma2d(base + OFF_RES + (i == RES1) * UNIT, &maps.x, cj * 128 + (i == RES1) * 64, rb * 128, bar_xres);
          }
          if (ps && i == 2) {
            mbar_wait(bar_ofree + (ps - 1) * 16, 0);
            if (elect_one()) bulk_load_stream(xd, xs, UNIT, bf);
          }
        }
        if (ps == 2) break;
        wch = ps ? ((wch >> 3) ^ rank) * 2 : wch + 4;
#pragma unroll 1
        for (int u = 0; u < 16; u++) {
          const bool isk = (u == 0) || ((u & 1) && u < 15), kept = (0x1680 >> u) & 1;
          const int blk = (0x472FAD84u >> (u * 2)) & 3;
          const uint32_t sl = base + unit_of(ps ? AT1 : AT0, u & 3) + rank * UNIT, bf = bfull + (u & 3) * 8;
          mbar_wait(bf, ((u >> 2) & 1) ^ 1);
          if (!kept && elect_one()) mbar_expect_tx(bf, SLOT_BYTES);
          mbar_wait(u < 4 ? gempty + ((u + 1) >> 1) * 8 : bempty + (u & 3) * 8, ((u >> 2) & 1) ^ 1);
          if (elect_one()) {
            if (kept) mbar_arrive(bf);
            else if (ps && (blk >= 2 || u > 8)) tma3d_mc<true>(sl, isk ? &maps.k : &maps.v, 0, kvrow + blk * 128, rank, bf);
            else tma3d_mc<false>(sl, isk ? &maps.k : &maps.v, 0, kvrow + blk * 128, rank, bf);
          }
        }
      }
      if (elect_one()) mbar_expect_tx(bar_rx, UNIT);
      mbar_wait(bar_rel, 0);
      if (elect_one()) {
        bulk_load_stream(base + UNIT, g_act + (uint32_t)(rb * 80 + 16 + 63 - (cj & 1) * 32) * UNIT, UNIT, bar_rx);
      }
      if (b < NFFN) {
#pragma unroll 1
        for (int u = 0; u < 12; u++) {
          const uint32_t dst = base + unit_of(u < 4 ? FT_G : (u < 8 ? FT_U : FT_D), u & 3);
          if (elect_one()) mbar_expect_tx(bar_box + u * 8, UNIT);
          if (u == 0 || u == 2 || u == 8) mbar_wait(bar_ring + (u == 8 ? 16 : u * 4), 0);
          const int fp = u < 8 ? FPACE0 : FPACE;
          if (u >= fp) mbar_wait(bar_box + (u - fp) * 8, 0);
          if (elect_one()) {
            if (u < 8) tma2d(dst, u < 4 ? &maps.wg : &maps.wu, b * 32, (u & 3) * 256, bar_box + u * 8);
            else tma3d(dst, &maps.wd, 0, b * 32, (u - 8) * 4, bar_box + u * 8);
          }
        }
      }
    } else if (warp == 9) {
      const uint32_t target = 8 * (epoch + 1);
      uint32_t hmask = 0;
#pragma unroll 1
      for (int i = 0; i < 16; i++) {
        if (i == HDX) mbar_wait(bar_mod, 0);
        const int kt = (2 * cj + slice_of(i)) & 15;
        const uint32_t need = i == 15 ? 0xffffu : 1u << kt;
        if (i >= NRS && (hmask & need) != need) {
          uint32_t n = 0;
          do { hmask = __ballot_sync(0xffffffffu, ld_acquire(&g_cnt_h[rb * 32 + (lane & 15)]) == epoch + 1); watchdog(n); } while ((hmask & need) != need);
          PROF(1, lane == 0 && i == NRS, 26);
          fence_async();
        }
        mbar_wait(xempty + (i & 3) * 8, ((i >> 2) & 1) ^ 1);
        if (elect_one()) {
          mbar_expect_tx(xfull + (i & 3) * 8, UNIT);
          if (i < NRS) tma2d(base + (i & 3) * GST_BYTES, &maps.x, kt * 64, rb * 128, xfull + (i & 3) * 8);
          else bulk_load_stream(base + (i & 3) * GST_BYTES, g_act + (uint32_t)(rb * 80 + kt) * UNIT, UNIT, xfull + (i & 3) * 8);
        }
      }
      prefetch_map(&maps.wo);
#pragma unroll 1
      for (int t = 0; t < 4; t++) {
        if (t & 1) mbar_wait(bar_od, t >> 1);
        const int ops = OPS >> (t & 1);
#pragma unroll 1
        for (int p = 0; p < 32768; p += ops) {
          const uint32_t w = p >> 14, c = (p >> 13) & 1, off = w * 8192 + (p & 8191);
          mbar_wait(bar_ofull + (t & 1) * 16 + w * 8, t >> 1);
          if (elect_one()) {
            bulk_store(g_act + (uint32_t)(rb * 80 + 16 + (cj * 4 + t) * 2 + c) * UNIT + off, base + unit_of(QT, 2 * t + c) + off, ops);
            asm volatile("cp.async.bulk.commit_group;" ::: "memory");
            asm volatile("cp.async.bulk.wait_group.read 0;" ::: "memory");
          }
        }
        if (elect_one()) {
          mbar_arrive(t < 3 ? bar_ofree + t * 8 : bar_res);
          asm volatile("cp.async.bulk.wait_group 0;" ::: "memory");
          fence_async();
          red_release(&g_cnt_o[((rb * 4 + t) * 2 + (cj >> 2)) * 32], 2);
        }
        if (t) {
          wait_counter(&g_cnt_o[(rb * 8 + 2 * t + (cj & 1)) * 32], target);
          if (t & 1) wait_counter(&g_cnt_o[(rb * 8 + (t == 1 ? cj & 1 : 7 - (cj & 1))) * 32], target);
          if (elect_one()) mbar_arrive(t == 1 ? bar_ofree + 24 : bar_cnt + t * 8 - 16);
        }
      }
      PROF(2, lane == 0, 27);
      const uint32_t tag = epoch % 3 + 1;
      const uint32_t* inbox = g_cand + (b >> 4) % CR * 512 + (lane & 15) * CS;
      mbar_wait(bar_ring + 16, 0);
      uint32_t c0 = ld_relaxed(inbox), n = 0;
#define CAND_STEP(cv)                                                                                        \
      {                                                                                                      \
        const bool valid = (cv & 3u) == tag, all = __all_sync(0xffffffffu, valid);                           \
        const uint32_t best = __reduce_max_sync(0xffffffffu, valid ? cv : 0u);                               \
        const uint32_t blk = __ffs(__ballot_sync(0xffffffffu, cv == best)) - 1;                              \
        if (best) sts2(par + PAR_CONST + 56, best, (blk << 7 | (~best >> 2 & 127)) | (all ? 0x1800 : 0x800)); \
        if (all) break;                                                                                      \
        cv = ld_relaxed(inbox);                                                                              \
      }
      while (true) { CAND_STEP(c0) watchdog(n); }
    } else {
      const int t2 = tid - 320;
      if (late && warp == 10) {
        mbar_wait(bar_hx, 0);
        if (elect_one()) {
          tma2d(stage, &maps.wm, (b >> 1) * 32, rank * 512, bar_hw);
          tma2d(stage + 16384, &maps.wm, (b >> 1) * 32, rank * 512 + 256, bar_hw);
        }
      }
      {
        const uint32_t tag = epoch % 3 + 1;
        mbar_wait(bar_hx + 8, 0);
        mbar_wait(bar_hw, 0);
        __nanosleep(late ? OSL2 : OSL);
        {
          const uint32_t t7 = (warp & 1) * 64 + (lane >> 4) * 32 + 16 + (lane & 15);
          const uint32_t* pm = g_modp + ((cj * 128 + t7 * 4) & (DM - 1));
          uint4 m0, m1, m2, m3;
          uint32_t n = 0;
          do {
            m0 = ld_relaxed4(pm); m1 = ld_relaxed4(pm + 2 * DM); m2 = ld_relaxed4(pm + DM); m3 = ld_relaxed4(pm + 3 * DM);
            watchdog(n);
          } while (!__all_sync(0xffffffffu, tag_ok(m0, tag) && tag_ok(m1, tag) && tag_ok(m2, tag) && tag_ok(m3, tag)));
          write_table(par, false, t7, m0, m1);
          write_table(par, true, t7, m2, m3);
          mbar_arrive(bar_mod2);
        }
      }
      mbar_wait(bar_hpub + (warp & 1) * 8, 0);
      PROF(1, t2 == 0, 24);
#pragma unroll 1
      for (int c = 0; c < 8; c++) {
        const uint32_t off = (warp & 1) * UNIT + c * 2048 + lane * 16;
        uint8_t* dst = g_act + (uint32_t)(rb * 80 + cj * 2) * UNIT + off;
        const uint4 v0 = lds4(stage + off), v1 = lds4(stage + off + 512), v2 = lds4(stage + off + 1024), v3 = lds4(stage + off + 1536);
        stg4(dst, v0); stg4(dst + 512, v1); stg4(dst + 1024, v2); stg4(dst + 1536, v3);
      }
      __syncwarp();
      PROF(1, t2 == 0, 15);
      if (lane == 0) {
        mbar_arrive(bar_pread);
        red_release(&g_cnt_h[rb * 32 + cj * 2 + (warp & 1)], 1);
        PROF(1, t2 == 0, 25);
        prefetch_map(&maps.wg); prefetch_map(&maps.wu); prefetch_map(&maps.wd); prefetch_map(&maps.out);
      }
      __syncwarp();
      if (b < NFFN) {
        mbar_wait(bar_go2, 0);
        const __nv_bfloat16* pg = ((b & 1) ? P.w_up : P.w_gate) + (b >> 1) * 64 + (size_t)t2 * FF;
        const __nv_bfloat16* pd = P.w_down + (size_t)b * 32768 + t2 * 64;
        PROF(2, t2 == 0, 13);
#pragma unroll 1
        for (int i = 0; i < WN; i += WB) {
          uint32_t v[WB];
#pragma unroll
          for (int u = 0; u < WB; u++) {
            const int k = i + u;
            asm volatile("ld.global.cg.L2::128B.u32 %0, [%1];" : "=r"(v[u]) : "l"(k < 16 ? pg + (size_t)k * 64 * FF : pd + (k - 16) * 4096));
          }
#pragma unroll
          for (int u = 1; u < WB; u++) v[0] ^= v[u];
          sts1(par + PAR_SINK + t2 * 4, v[0]);
        }
        PROF(2, t2 == 0, 14);
      }
      const uint32_t tag = epoch % 3 + 1;
      mbar_wait(bar_go, 0);
      bar_sync(4, 64);
      if (warp == 10) {
        const uint32_t* src = g_mod + 2 * DM + cj * 128 + lane * 4;
        const uint2 wr = *reinterpret_cast<const uint2*>(P.w_r + cj * 128 + lane * 4);
        uint4 vga, vsb, vcb, vgb;
        uint32_t n = 0;
        do {
          vga = ld_relaxed4(src); vsb = ld_relaxed4(src + DM); vcb = ld_relaxed4(src + 2 * DM); vgb = ld_relaxed4(src + 3 * DM);
          watchdog(n);
        } while (!__all_sync(0xffffffffu, tag_ok(vga, tag) && tag_ok(vsb, tag) && tag_ok(vcb, tag) && tag_ok(vgb, tag)));
        const float c0 = rbf(1.f + bf_hi(vcb.x)), c1 = rbf(1.f + bf_hi(vcb.y)), c2 = rbf(1.f + bf_hi(vcb.z)), c3 = rbf(1.f + bf_hi(vcb.w));
        const float a0 = c0 * bf_lo(wr.x), a1 = c1 * bf_hi(wr.x), a2 = c2 * bf_lo(wr.y), a3 = c3 * bf_hi(wr.y);
        const uint32_t h0 = pack_bf(a0, a1), h1 = pack_bf(a2, a3);
        const uint32_t t1 = par + PAR_T1 + (lane >> 2) * 64 + (lane & 1) * 32 + (lane & 2) * 2;
        sts1(t1, h0); sts1(t1 + 8, pack_bf(a0 - bf_lo(h0), a1 - bf_hi(h0)));
        sts1(t1 + 16, h1); sts1(t1 + 24, pack_bf(a2 - bf_lo(h1), a3 - bf_hi(h1)));
        const uint32_t tg = par + PAR_SINK + (lane >> 3) * 64 + (lane & 1) * 32 + (lane & 6) * 2;
        sts1(tg, __byte_perm(vga.x, vga.y, 0x7632)); sts1(tg + 16, __byte_perm(vga.z, vga.w, 0x7632));
        sts4(par + PAR_T2 + lane * 32, make_uint4(pack_bf(c0, c1), __byte_perm(vsb.x, vsb.y, 0x7632), __byte_perm(vgb.x, vgb.y, 0x7632), __byte_perm(vga.x, vga.y, 0x7632)));
        sts4(par + PAR_T2 + lane * 32 + 16, make_uint4(pack_bf(c2, c3), __byte_perm(vsb.z, vsb.w, 0x7632), __byte_perm(vgb.z, vgb.w, 0x7632), __byte_perm(vga.z, vga.w, 0x7632)));
      } else {
        const uint4 g = poll4((lane & 8) ? g_mod + 8 - (lane & 1) * 4 : g_mod + 5 * DM + (b >> 4) * 128 + (lane & 7) * 16 + (b & 12), tag);
        sts1(par + PAR_CONST + 60, 0);
        if (lane < 8) sts1(par + PAR_CONST + 16 + lane * 4, (b & 2) ? ((b & 1) ? g.w : g.z) : ((b & 1) ? g.y : g.x));
        else if (lane < 10) sts2(par + PAR_CONST + (lane - 8) * 8, __float_as_uint(untag_sum(g.x, g.y) + untag_sum(g.z, g.w)), epoch);
      }
      __syncwarp();
#pragma unroll 1
      for (int q = 0; q < 32; q++) {
        st_b128(g_xch + ((size_t)b * 8 * 256 + q * 64 + t2) * 4, (epoch & 1) << 16, 0, 0, 0);
        __nanosleep(RSL);
      }
      for (int q = 0; q < 2; q++) st_relaxed4(g_stats + (((rb * 8 + q * 4 + (t2 >> 4)) * 8 + cj) * 16 + (t2 & 15)) * 4, 0, 0, 0, 0);
      if (b < NFFN)
        for (int q = 0; q < 2; q++) st_relaxed4(ypart_slot(b, q * 64 + t2), 0, 0, 0, 0);
      st_relaxed4(g_row + rb * 2 * DM + (t2 >> 5) * DM + cj * 128 + (t2 & 31) * 4, 0, 0, 0, 0);
      __threadfence();
      mbar_arrive(bar_par);
      mbar_wait(bar_gate, 0);
      uint32_t have = 0, n = 0;
      while (true) {
        const uint32_t st = lds1(par + PAR_CONST + 60) >> 7;
        if ((st & 31) != have) {
          const uint32_t* hsrc = g_row + (st & 15) * 2 * DM + t2 * 4;
          uint4 hv[4];
          bool ok = true;
#pragma unroll
          for (int i = 0; i < 4; i++) hv[i] = ld_pairs(hsrc + i * 256);
#pragma unroll
          for (int i = 0; i < 4; i++) {
            sts2(base + ((FT_G >> i * 4) & 15) * UNIT + (warp & 1) * 8192 + 256 + lane * 8, hv[i].x, hv[i].z);
            ok = ok && hv[i].y == tag && hv[i].w == tag;
          }
          have = __all_sync(0xffffffffu, ok) ? st & 31 : 0;
        }
        if ((st ^ have) == 32) break;
        watchdog(n);
      }
      mbar_arrive(bar_sel);
    }
    __syncwarp();
    cluster_arrive();
    {
      const uint32_t tag = epoch % 3 + 1, t3 = tid - 256;
      mbar_wait(bar_win, 0);
      uint2 win = lds2(par + PAR_CONST + 56);
      win.y &= 0x7ff;
      const uint32_t* fsrc = g_row + (win.y >> 7) * 2 * DM + (b >> 4) * 128 + (t3 & 7) * 16 + (b & 6) * 2 + ((b >> 2) & 2);
      const uint32_t* ysrc = ypart_slot(min(t3, NFFN - 1), b);
      uint2 fh = ld_pair(fsrc), fx = ld_pair(fsrc + DM);
      uint4 ya = ld_b128(ysrc);
      const float rwin = __uint_as_float(((int)win.x < 0 ? win.x & 0x7fffffffu : ~win.x) & ~0x1ffu);
      const float rs = rbf(rcp(1.f + __expf(-rbf(rwin))));
      uint32_t n = 0;
      while (__any_sync(0xffffffffu, fh.y != tag || fx.y != tag)) { fh = ld_pair(fsrc); fx = ld_pair(fsrc + DM); watchdog(n); }
      while (true) {
        const bool miss = ((ya.x & 1) | (ya.y & 1) << 1) != tag;
        if (!__any_sync(0xffffffffu, miss)) break;
        if (miss) ya = ld_b128(ysrc);
        watchdog(n);
      }
      PROF(8, t3 == 0, 5);
      float y[8] = {bf_lo(ya.x & ~1u), bf_hi(ya.x), bf_lo(ya.y & ~1u), bf_hi(ya.y), bf_lo(ya.z), bf_hi(ya.z), bf_lo(ya.w), bf_hi(ya.w)};
#pragma unroll
      for (int h = 4; h > 0; h >>= 1) {
        const bool up = lane & (h * 2);
#pragma unroll
        for (int e = 0; e < h; e++) y[e] = (up ? y[e + h] : y[e]) + __shfl_xor_sync(0xffffffffu, up ? y[e] : y[e + h], h * 2);
      }
      y[0] += __shfl_xor_sync(0xffffffffu, y[0], 1);
      if (!(lane & 1)) sts1(par + PAR_RED + 64 + t3 * 2, __float_as_uint(y[0]));
      bar_sync(4, 128);
      if (t3 < 8) {
        float y0 = 0.f;
#pragma unroll
        for (int w7 = 0; w7 < 7; w7++) y0 += __uint_as_float(lds1(par + PAR_RED + 64 + w7 * 32 + t3 * 4));
        const uint32_t gv = lds1(par + PAR_CONST + 16 + t3 * 4);
        const uint32_t upd = hmul2(pack_bf(y0, y0), pack_bf(rs, rs));
        const uint32_t r = hadd2(fx.x, hmul2(__byte_perm(gv, gv, 0x3232), hadd2(fh.x, upd)));
        reinterpret_cast<uint16_t*>(P.out)[(size_t)win.y * DM + (b >> 4) * 128 + t3 * 16 + (b & 15)] = (b & 1) ? r >> 16 : r;
        if (b == 0 && t3 == 0) st_relaxed(&g_epoch, epoch + 1);
      }
      PROF(31, t3 == 0, 36);
    }
    cluster_wait();
  } else {
    const int wg = warp >> 2;

    uint32_t tag;
    auto gemv = [&]() {
      const uint32_t l = fresh_lane(), fr = (l & 7) + (l >> 4) * 8, tq = l & 3, row = base + 2 * GST_BYTES + warp * 2048;
      const uint32_t wa = stage + warp * 4096 + fr * 64 + ((((l >> 3) & 1) ^ ((fr >> 1) & 3)) << 4);
      uint32_t sc[8];
#pragma unroll
      for (int k = 0; k < 8; k++) sc[k] = lds1(row + 128 + k * 16 + tq * 4);
      float d0[4] = {0.f, 0.f, 0.f, 0.f}, d1[4] = {0.f, 0.f, 0.f, 0.f};
      mbar_wait(bar_hw, 0);
#pragma unroll
      for (int ks = 0; ks < 4; ks++) {
        uint32_t w[8];
        ldmatrix4t(wa + ks * 1024, w[0], w[1], w[2], w[3]);
        ldmatrix4t((wa ^ 32) + ks * 1024, w[4], w[5], w[6], w[7]);
        mma16816(d0, w[0], w[1], w[2], w[3], sc[2 * ks], sc[2 * ks + 1]);
        mma16816(d1, w[4], w[5], w[6], w[7], sc[2 * ks], sc[2 * ks + 1]);
      }
      sts1(row + (tq * 8 + (l >> 2)) * 4, __float_as_uint((tq & 2) ? ((tq & 1) ? d1[2] : d1[0]) : ((tq & 1) ? d0[2] : d0[0])));
      bar_sync(1, 256);
      if (warp == 0) {
        float s = 0.f;
#pragma unroll
        for (int w8 = 0; w8 < 8; w8++) s += __uint_as_float(lds1(row + w8 * 2048 + l * 4));
        st_relaxed(g_modp + rank * 2 * DM + (b >> 1) * 32 + l, (__float_as_uint(s) & ~3u) | tag);
      }
      PROF(1, tid == 0, 3);
    };
    {
      uint32_t* const pmod = g_modp + rank * 2 * DM + (b >> 1) * 32 + lane;
      uint32_t* const pln = g_ln1 + (rb * 128 + cj * 16 + warp) * 4;
      const uint32_t cv = ldg_nc1(P.c + rank * 512 + tid * 2);
      const uint32_t epoch = ld_relaxed(&g_epoch);
      if (warp == 0) st_relaxed(pmod, 0);
      if (lane == 0) { st_b128(pln, 0, 0, 0, 0); st_b128(pln + 32, 0, 0, 0, 0); }
      asm volatile("setmaxnreg.inc.sync.aligned.u32 232;");
      bar_sync(1, 320);
      tag = epoch % 3 + 1;
#pragma unroll
      for (int part = 0; part < 3; part++) {
        if (!(part & 1)) {
          const uint32_t xa = base + (2 + part / 2) * GST_BYTES + warp * 2048 + lane * 16;
          mbar_wait(bar_hx + part * 4, 0);
          float s0 = 0.f, s1 = 0.f, q0 = 0.f, q1 = 0.f;
#pragma unroll
          for (int q = 0; q < 4; q++) {
            const uint4 xv = lds4(xa + q * 512);
            const uint32_t u[4] = {xv.x, xv.y, xv.z, xv.w};
#pragma unroll
            for (int e = 0; e < 4; e++) { const float lo = bf_lo(u[e]), hi = bf_hi(u[e]); s0 += lo; s1 += hi; q0 += lo * lo; q1 += hi * hi; }
          }
          s0 += s1; q0 += q1;
#pragma unroll
          for (int o = 16; o > 0; o >>= 1) { s0 += __shfl_xor_sync(0xffffffffu, s0, o); q0 += __shfl_xor_sync(0xffffffffu, q0, o); }
          const float mean = s0 * (1.f / DM);
          float mb, sd;
          ln_scalars(mean, fmaxf(q0 * (1.f / DM) - mean * mean, 0.f), mb, sd);
          uint32_t ih, il;
          split_inv(sd, ih, il);
          if (lane == 0) st_b128(pln + part * 16, pack_bf(mb, mb), ih, il, tag);
          PROF(1, tid == 0 && part == 2, 4);
        } else {
          __syncwarp();
          sts1(base + 2 * GST_BYTES + warp * 2048 + 128 + lane * 4, pack_bf(silu_f(bf_lo(cv)), silu_f(bf_hi(cv))));
          __syncwarp();
          if (!late) gemv();
        }
      }
      cluster_wait();
      if (wg == 1) bar_arrive(2, 256);
    }

    const uint32_t rempty = lane < 2 ? mapa(bempty, lane & 1) : 0;
    constexpr uint32_t GE = NSLOT * 8 + 32;
    float o[64], s[64];
#pragma unroll 1
    for (int ps = 0; ps < 3; ps++) {
      {
        const uint32_t xt = ps == 1 ? XT1 : XT2, wt = ps == 1 ? WT1 : WT2;
        const int nst = ps == 2 ? 28 : 14;
        if (ps == 0) {
          float ga[64], gb[64];
#pragma unroll
          for (int i = 0; i < 64; i++) { ga[i] = 0.f; gb[i] = 0.f; }
          uint32_t a[2][16];
          const uint32_t l = fresh_lane();
          uint32_t fa[4];
#pragma unroll
          for (int kk = 0; kk < 4; kk++) fa[kk] = (base + wg * 8192 + frag_offset(warp)) ^ (kk * 32);
          const uint32_t mt = par + (l & 3) * 16;
          auto fetch = [&](int i, uint32_t (&f)[16], uint32_t z) {
            mbar_wait(xfull + (i & 3) * 8, i >> 2);
#pragma unroll
            for (int kk = 0; kk < 4; kk++) ldmatrix4(fa[kk] + (i & 3) * GST_BYTES + z, f[4 * kk], f[4 * kk + 1], f[4 * kk + 2], f[4 * kk + 3]);
          };
          const bool oddw = warp & 2;
          uint4 r0, r1;
          {
            const uint32_t t7 = (warp & 1) * 64 + (l >> 4) * 32 + (l & 15);
            const uint32_t* pm = g_modp + wg * DM + ((cj * 128 + t7 * 4) & (DM - 1));
            const uint32_t* pr = g_ln1 + (rb * 128 + warp * 16 + (l >> 2)) * 4;
            uint4 m0 = make_uint4(tag, tag, tag, tag), m1 = m0;
            if (late) gemv();
            if (!oddw) { m0 = ld_relaxed4(pm); m1 = ld_relaxed4(pm + 2 * DM); }
            r0 = ld_b128(pr); r1 = ld_b128(pr + 32);
            fetch(0, a[0], 0); fetch(1, a[1], 0);
            uint32_t n = 0;
            bool written = false;
#pragma unroll 1
            while (true) {
              uint32_t miss;
              asm volatile("{ .reg .pred p0, p1, p2, p3; .reg .b32 t, u;\n"
                           "lop3.b32 t, %1, %2, %19, 0x7e; lop3.b32 u, %3, %4, %19, 0x7e; or.b32 t, t, u; and.b32 t, t, 3; setp.ne.u32 p0, t, 0;\n"
                           "lop3.b32 t, %5, %6, %19, 0x7e; lop3.b32 u, %7, %8, %19, 0x7e; or.b32 t, t, u; and.b32 t, t, 3; setp.ne.u32 p1, t, 0;\n"
                           "setp.ne.u32 p2, %12, %19; setp.ne.u32 p3, %16, %19;\n"
                           "@p0 ld.relaxed.gpu.global.v4.u32 {%1, %2, %3, %4}, [%17];\n"
                           "@p1 ld.relaxed.gpu.global.v4.u32 {%5, %6, %7, %8}, [%17 + 8192];\n"
                           "@p2 ld.relaxed.gpu.global.v4.u32 {%9, %10, %11, %12}, [%18];\n"
                           "@p3 ld.relaxed.gpu.global.v4.u32 {%13, %14, %15, %16}, [%18 + 128];\n"
                           "or.pred p0, p0, p1; or.pred p2, p2, p3; vote.sync.any.pred p0, p0, 0xffffffff; vote.sync.any.pred p2, p2, 0xffffffff;\n"
                           "selp.u32 t, 1, 0, p0; selp.u32 u, 2, 0, p2; or.b32 %0, t, u; }"
                           : "=r"(miss), "+r"(m0.x), "+r"(m0.y), "+r"(m0.z), "+r"(m0.w), "+r"(m1.x), "+r"(m1.y), "+r"(m1.z), "+r"(m1.w),
                             "+r"(r0.x), "+r"(r0.y), "+r"(r0.z), "+r"(r0.w), "+r"(r1.x), "+r"(r1.y), "+r"(r1.z), "+r"(r1.w)
                           : "l"(pm), "l"(pr), "r"(tag) : "memory");
              if (!(miss & 1) && !written) {
                written = true;
                if (!oddw) write_table(par, wg, t7, m0, m1);
                mbar_arrive(bar_mod);
              }
              if (!miss) break;
              watchdog(n);
            }
          }
          const uint32_t zero = r0.w ^ tag;
          auto normalize = [&](uint32_t (&f)[16]) {
#pragma unroll
            for (int k = 0; k < 16; k += 2) { f[k] = ln_norm(f[k], r0.x, r0.y, r0.z); f[k + 1] = ln_norm(f[k + 1], r1.x, r1.y, r1.z); }
          };
          auto modulate = [&](int i, uint32_t (&f)[16]) {
#pragma unroll
            for (int kk = 0; kk < 4; kk++) {
              const uint4 m = lds4(mt + slice_of(i) * 256 + kk * 64);
              f[4 * kk] = hfma2(f[4 * kk], m.x, m.z); f[4 * kk + 1] = hfma2(f[4 * kk + 1], m.x, m.z);
              f[4 * kk + 2] = hfma2(f[4 * kk + 2], m.y, m.w); f[4 * kk + 3] = hfma2(f[4 * kk + 3], m.y, m.w);
            }
            keep(f);
            mbar_arrive_pred(xempty + (i & 3) * 8, l == 0);
          };
          auto publish = [&](int u, uint32_t (&f)[16]) {
#pragma unroll
            for (int kk = 0; kk < 4; kk++) stmatrix4(fa[kk] + OFF_STAGE + u * UNIT, f[4 * kk], f[4 * kk + 1], f[4 * kk + 2], f[4 * kk + 3]);
            __syncwarp();
            mbar_arrive_pred(bar_hpub + u * 8, l == 0);
          };
          auto multiply = [&](int i, uint32_t (&f)[16]) {
            mbar_wait(gfull + (i & 3) * 8, i >> 2);
            const uint64_t db = make_desc(base + (i & 3) * GST_BYTES + UNIT, 8192, 1024);
            wg_fence();
#pragma unroll
            for (int kk = 0; kk < 4; kk++) mma256_rs(ga, gb, f[4 * kk], f[4 * kk + 1], f[4 * kk + 2], f[4 * kk + 3], db + kk * 128);
            wg_commit();
          };
          auto next = [&](int i, uint32_t (&f)[16]) {
            wg_wait<1>();
            mbar_arrive_cl(rempty, GE + ((i + 2) & 3) * 8);
            uint32_t z = zero;
#pragma unroll
            for (int k = 0; k < 16; k += 2) asm volatile("lop3.b32 %0, %1, %2, %0, 0xA8;" : "+r"(z) : "r"(f[k]), "r"(f[k + 1]));
            fetch(i, f, z);
            normalize(f);
            if (i == 3) { keep(f); mbar_wait(bar_mod2, 0); }
            modulate(i, f); multiply(i, f);
          };
          normalize(a[0]);
          keep(a[0]); keep(a[1]);
          mbar_wait(bar_mod, 0);
          PROF(1, tid == 0, 2);
          modulate(0, a[0]); multiply(0, a[0]); publish(0, a[0]);
          keep(a[1]);
          normalize(a[1]);
          modulate(1, a[1]); multiply(1, a[1]);
#pragma unroll 1
          for (int i = 2; i < NRS; i += 2) {
            next(i, a[0]);
            next(i + 1, a[1]);
            if (i == 2) publish(1, a[1]);
          }
          wg_wait<1>();
          mbar_arrive_cl(rempty, GE + ((NRS + 2) & 3) * 8);
#pragma unroll 1
          for (int i = NRS; i < 14; i++) {
            mbar_wait(xfull + (i & 3) * 8, (i >> 2) & 1);
            mbar_wait(gfull + (i & 3) * 8, (i >> 2) & 1);
            const uint32_t xa = base + (i & 3) * GST_BYTES;
            const uint64_t da = make_desc(xa + wg * 8192, 16, 1024), db = make_desc(xa + UNIT, 8192, 1024);
            if (i == 13) bar_sync(2 + wg, 256);
            wg_fence();
#pragma unroll
            for (int kk = 0; kk < 4; kk++) mma256_ss(ga, gb, da + kk * 2, db + kk * 128, 1);
            wg_commit();
            if (i == 13) bar_arrive(3 - wg, 256);
            wg_wait<1>();
            uint32_t z = zero;
#pragma unroll
            for (int k = 0; k < 16; k += 2) asm volatile("lop3.b32 %0, %1, %2, %0, 0xA8;" : "+r"(z) : "r"(a[1][k]), "r"(a[1][k + 1]));
            mbar_arrive_cl(rempty, GE + ((i + 3) & 3) * 8 + z);
            mbar_arrive_pred(xempty + ((i + 3) & 3) * 8, l == 0 && i != NRS);
          }
          mbar_wait(xfull + 16, 1);
          wg_wait<0>();
          keep(ga); keep(gb);
#pragma unroll
          for (int i = 0; i < 64; i++) {
            asm volatile("mov.b32 %0, %1;" : "=f"(s[i]) : "f"(ga[i]));
            asm volatile("mov.b32 %0, %1;" : "=f"(o[i]) : "f"(gb[i]));
          }
        } else {
          float ga[64], gb[64];
#pragma unroll
          for (int i = 0; i < 64; i++) {
            asm volatile("mov.b32 %0, %1;" : "=f"(ga[i]) : "f"(s[i]));
            asm volatile("mov.b32 %0, %1;" : "=f"(gb[i]) : "f"(o[i]));
          }
#pragma unroll 1
          for (int i = 0; i < nst; i++) {
            mbar_wait(gfull + (i & 3) * 8, (i >> 2) & 1);
            const uint64_t da = make_desc(base + unit_of(xt, i & 3) + wg * 8192, 16, 1024), db = make_desc(base + unit_of(wt, i & 3), 8192, 1024);
            if (i == nst - 1) bar_sync(2 + wg, 256);
            wg_fence();
#pragma unroll
            for (int kk = 0; kk < 4; kk++) mma256_ss(ga, gb, da + kk * 2, db + kk * 128, kk ? 1 : i);
            wg_commit();
            if (i == nst - 1) bar_arrive(3 - wg, 256);
            wg_wait<1>();
            mbar_arrive_cl(rempty, GE + ((i + 3) & 3) * 8, i != 0);
            PROF(4, tid == 0 && (i & 3) == 0, 40 + (ps - 1) * 4 + i / 4);
          }
          wg_wait<0>();
          keep(ga); keep(gb);
#pragma unroll
          for (int i = 0; i < 64; i++) {
            asm volatile("mov.b32 %0, %1;" : "=f"(s[i]) : "f"(ga[i]));
            asm volatile("mov.b32 %0, %1;" : "=f"(o[i]) : "f"(gb[i]));
          }
        }
        mbar_arrive_cl(rempty, GE + (ps == 2 ? 24 : 8));
        if (ps == 2) break;
      }
      const uint32_t qw = base + wg * 8192, qt = QT >> (16 * ps), at = ps ? AT1 : AT0;
      {
        const uint32_t wt = ps ? WT1 : WT0;
        const uint64_t da0 = make_desc(qw + unit_of(qt, 2), 16, 1024), da1 = make_desc(qw + unit_of(qt, 3), 16, 1024);
        const uint64_t db0 = make_desc(base + unit_of(wt, 2), 8192, 1024), db1 = make_desc(base + unit_of(wt, 3), 8192, 1024);
        mbar_wait(gfull + 16, 1);
        bar_sync(2 + wg, 256);
        wg_fence();
#pragma unroll
        for (int kk = 0; kk < 4; kk++) mma_ss<1>(s, da0 + kk * 2, db0 + kk * 128, 1);
        wg_commit();
        mbar_wait(xfull + 24, 1);
        mbar_wait(gfull + 24, 1);
        wg_fence();
#pragma unroll
        for (int kk = 0; kk < 4; kk++) mma_ss<1>(s, da1 + kk * 2, db1 + kk * 128, 1);
        wg_commit();
        bar_arrive(3 - wg, 256);
        mbar_wait(ps == 0 ? bar_pread : bar_ofree + 8, 0);
        wg_wait<0>();
        keep(s);
        PROF(2, tid == 0, 8 + ps * 8);
        uint32_t q[32];
        pack_p(s, q);
#pragma unroll
        for (int i = 0; i < 4; i++) stmatrix4((qw + unit_of(qt, 0) + frag_offset(warp)) ^ (i << 5), q[4 * i], q[4 * i + 1], q[4 * i + 2], q[4 * i + 3]);
        keep(q);
        bar_sync(2 + wg, 256);
        wg_fence();
#pragma unroll
        for (int kk = 0; kk < 8; kk++) mma_ss<1>(o, (kk < 4 ? da0 : da1) + (kk & 3) * 2, (kk < 4 ? db0 : db1) + UNIT / 16 + (kk & 3) * 128, 1);
        wg_commit();
        mbar_wait(bfull, 0);
        wg_fence();
        const uint64_t dk = make_desc(base + unit_of(at, 0), 16, 1024);
#pragma unroll
        for (int kk = 0; kk < 8; kk++) mma_rs<0>(s, q[4 * kk], q[4 * kk + 1], q[4 * kk + 2], q[4 * kk + 3], dk + (kk >> 2) * 1024 + (kk & 3) * 2, kk != 0);
        wg_commit();
        bar_arrive(3 - wg, 256);
#pragma unroll
        for (int i = 4; i < 8; i++) stmatrix4((qw + unit_of(qt, 1) + frag_offset(warp)) ^ ((i & 3) << 5), q[4 * i], q[4 * i + 1], q[4 * i + 2], q[4 * i + 3]);
        wg_wait<1>();
        keep(o);
        mbar_arrive_cl(rempty, GE + 16);
        mbar_arrive_cl(rempty, GE + 24);
        store_chunk<0>(o, qw + unit_of(qt, 2) + frag_offset(warp));
        store_chunk<1>(o, qw + unit_of(qt, 3) + frag_offset(warp));
        wg_wait<0>();
        keep(s);
        mbar_arrive_cl(rempty, 0);
      }
      PROF(4, tid == 0 && ps == 1, 61);
      float l0 = 0.f, l1 = 0.f, f0 = 0.f, f1 = 0.f;
      auto step = [&](auto odd_c, const int j, uint32_t (&pw)[32], uint32_t (&pr)[32]) {
        constexpr bool ODD = decltype(odd_c)::value;
        const bool first = !ODD && (j & 2) == 0, last = ODD && j == 7;
        const uint32_t ph = (j >> 1) & 1;
        float i0, i1, a0, a1;
        const bool so = !ODD && j == 4;
        if (so) { i0 = inv_quad_sum(l0); i1 = inv_quad_sum(l1); l0 = 0.f; l1 = 0.f; }
        if (first) {
          int m0 = max(__float_as_int(s[0]), __float_as_int(s[1])), m1 = max(__float_as_int(s[2]), __float_as_int(s[3]));
#pragma unroll
          for (int i = 1; i < 16; i++) {
            m0 = __vimax3_s32(m0, __float_as_int(s[4 * i]), __float_as_int(s[4 * i + 1]));
            m1 = __vimax3_s32(m1, __float_as_int(s[4 * i + 2]), __float_as_int(s[4 * i + 3]));
          }
          m0 = max(m0, __shfl_xor_sync(0xffffffffu, m0, 1)); m1 = max(m1, __shfl_xor_sync(0xffffffffu, m1, 1));
          m0 = max(m0, __shfl_xor_sync(0xffffffffu, m0, 2)); m1 = max(m1, __shfl_xor_sync(0xffffffffu, m1, 2));
          f0 = fmaf(__int_as_float(m0), SCL2, BIAS); f1 = fmaf(__int_as_float(m1), SCL2, BIAS);
        }
        bool redo = false;
        while (true) {
          if (redo) {
            float m0 = fmaxf(s[0], s[1]), m1 = fmaxf(s[2], s[3]);
#pragma unroll
            for (int i = 1; i < 16; i++) { m0 = fmaxf(m0, fmaxf(s[4 * i], s[4 * i + 1])); m1 = fmaxf(m1, fmaxf(s[4 * i + 2], s[4 * i + 3])); }
            m0 = fmaxf(m0, __shfl_xor_sync(0xffffffffu, m0, 1)); m1 = fmaxf(m1, __shfl_xor_sync(0xffffffffu, m1, 1));
            m0 = fmaxf(m0, __shfl_xor_sync(0xffffffffu, m0, 2)); m1 = fmaxf(m1, __shfl_xor_sync(0xffffffffu, m1, 2));
            m0 = fmaf(m0, SCL2, BIAS); m1 = fmaf(m1, SCL2, BIAS);
            if (!first) {
              m0 = fmaxf(m0, f0); m1 = fmaxf(m1, f1);
              const float c0 = ex2(f0 - m0), c1 = ex2(f1 - m1);
              l0 *= c0; l1 *= c1;
              wg_wait<0>();
              keep(o);
#pragma unroll
              for (int i = 0; i < 16; i++) { o[4 * i] *= c0; o[4 * i + 1] *= c0; o[4 * i + 2] *= c1; o[4 * i + 3] *= c1; }
            }
            f0 = m0; f1 = m1;
          }
          float b0 = 0.f, b1 = 0.f;
          a0 = 0.f; a1 = 0.f;
#pragma unroll
          for (int i = 0; i < 16; i++) {
            const float e0 = ex2(fmaf(s[4 * i], SCL2, -f0)), e1 = ex2(fmaf(s[4 * i + 1], SCL2, -f0));
            const float e2 = ex2(fmaf(s[4 * i + 2], SCL2, -f1)), e3 = ex2(fmaf(s[4 * i + 3], SCL2, -f1));
            a0 += e0; b0 += e1; a1 += e2; b1 += e3;
            pw[2 * i] = pack_bf(e0, e1); pw[2 * i + 1] = pack_bf(e2, e3);
            if (i == VREL) {
#pragma unroll
              for (int k = 0; k < 2 * VREL + 2; k++) asm volatile("" : "+r"(pw[k])::"memory");
              mbar_wait(bar_mod, 0);
              wg_wait<0>();
              mbar_arrive_cl(rempty, ODD ? 16 : 0, !redo && (ODD || j));
#pragma unroll
              for (int k = 4 * VREL + 4; k < 64; k++) asm volatile("" : "+f"(s[k])::"memory");
            }
          }
          a0 += b0; a1 += b1;
          if (redo) break;
          redo = __any_sync(0xffffffffu, !(a0 + a1 < 1.f));
          if (!redo) break;
        }
        l0 += a0; l1 += a1;
        keep(pw);
        keep(o);
        if (so) store_chunk<0>(o, i0, i1, qw + unit_of(qt, 0) + frag_offset(warp));
        keep(o);
        if (j == (ODD ? 5 : 0)) { fence_async_smem(); if (ODD) mbar_arrive(bar_ofull + wg * 8); }
        mbar_wait(bfull + (ODD ? 24 : 8), ph);
        bar_sync(2 + wg, 256);
        if (!last) {
          const uint32_t qn = qt >> (j >= 3 ? 8 : 0);
          wg_fence();
          issue_qk(s, qw + unit_of(qn, 0), qw + unit_of(qn, 1), base + unit_of(at, ODD ? 3 : 1));
          wg_commit();
          mbar_wait(bfull + (ODD ? 0 : 16), ODD ? ph ^ 1 : ph);
        }
        if (so) { store_chunk<1>(o, i0, i1, qw + unit_of(qt, 1) + frag_offset(warp)); keep(o); }
        wg_fence();
        issue_pv(o, pw, base + unit_of(at, ODD ? (last ? 3 : 0) : 2), !first);
        wg_commit();
        bar_arrive(3 - wg, 256);
        wg_wait<1>();
        keep(s);
        mbar_arrive_cl(rempty, ODD ? 24 : 8, !last);
        PROF(4, tid == 0 && ps == 1, 51 + j);
      };
      uint32_t pa[32], pb[32];
#pragma unroll 1
      for (int j = 0; j < 8; j += 2) {
        step(std::false_type{}, j, pa, pb);
        step(std::true_type{}, j + 1, pb, pa);
      }
      {
        const float i0 = inv_quad_sum(l0), i1 = inv_quad_sum(l1);
        wg_wait<0>();
        keep(o);
        mbar_arrive_cl(rempty, 24);
        store_chunk<0>(o, i0, i1, qw + unit_of(qt, 2) + frag_offset(warp));
        store_chunk<1>(o, i0, i1, qw + unit_of(qt, 3) + frag_offset(warp));
        fence_async_smem();
        mbar_arrive(bar_ofull + 16 + wg * 8);
      }
      PROF(2, tid == 0, 10 + ps * 8);
    }

    const int ln = fresh_lane(), g = ln >> 2, tq = ln & 3, ct = warp * 32 + ln;
    const bool lane0 = ln == 0;
    const int lrow0 = warp * 16 + g;
    const uint32_t res = base + OFF_RES, trow = res + wg * 8192 + frag_offset(warp);
    uint32_t xr[32];
    uint4 sv[4], own;
    uint32_t* const sg = g_stats + (rb * 8 + warp) * 512 + g * 4;
    uint32_t* sp[4];
#pragma unroll
    for (int k = 0; k < 4; k++) sp[k] = sg + (tq & 1) * 32 + (((tq >> 1) ^ (cj >> 2)) * 4 + (k ^ (cj & 3))) * 64;
    {
      const uint64_t da = make_desc(base + wg * 8192, 16, 1024), db = make_desc(base, 8192, 1024);
      constexpr int U = UNIT / 16;
#define HALF_STAGE(acc, xu, wu) _Pragma("unroll") for (int kk = 0; kk < 4; kk++) mma_ss<1>(acc, da + (xu) * U + kk * 2, db + (wu) * U + kk * 128, 1)
      PROF(10, ct == PT, 19); STAMP(0);
      cluster_arrive();
      mbar_wait(gfull, 1);
      mbar_wait(gfull + 8, 1);
      bar_sync(2 + wg, 256);
      wg_fence();
      HALF_STAGE(o, 7, 1);
      HALF_STAGE(o, 8, 3);
      wg_commit();
      STAMP(16);
      mbar_wait(gfull + 16, 1);
      STAMP(17);
      wg_fence();
      HALF_STAGE(o, 6, 11);
      wg_commit();
      bar_arrive(3 - wg, 256);
      mbar_wait(bar_par, 0);
      uint32_t* xo = g_xch + ((size_t)b * 8 * 256 + ct) * 4;
      const uint32_t* xi = g_xch + ((size_t)(b ^ 2) * 8 * 256 + ct) * 4;
      const uint32_t par1 = (~lds1(par + PAR_CONST + 4) & 1) << 16;
      wg_wait<1>();
      mbar_arrive_pred(bar_rel, lane0);
      wg_wait<0>();
      keep(o);
      mbar_arrive_pred(bar_ring, lane0);
      PROF(8, ct == PT, 20); STAMP(1);
#define SEND(i) st_b128(xo + (i) * 1024, (pack_bf(o[8 * (i)], o[8 * (i) + 1]) & ~0x10000u) | par1, pack_bf(o[8 * (i) + 2], o[8 * (i) + 3]), \
                        pack_bf(o[8 * (i) + 4], o[8 * (i) + 5]), pack_bf(o[8 * (i) + 6], o[8 * (i) + 7]))
#pragma unroll
      for (int i = 0; i < NS1; i++) SEND(i);
      PROF(8, ct == PT, 21); STAMP(2);
      bar_sync(2 + wg, 256);
      wg_fence();
      HALF_STAGE(s, 7, 0);
      HALF_STAGE(s, 8, 2);
      HALF_STAGE(s, 6, 10);
      wg_commit();
      bar_arrive(3 - wg, 256);
      STAMP(18);
      mbar_wait(gfull + 24, 1);
#pragma unroll
      for (int i = NS1; i < 8; i++) SEND(i);
      uint4 v[8];
      STAMP(19);
      mbar_wait(bar_xres, 0);
      wg_wait<0>();
      mbar_arrive_pred(bar_ring + 8, lane0);
      bar_sync(2 + wg, 256);
      STAMP(20);
#pragma unroll
      for (int i = 0; i < LD2; i++) v[i] = ld_b128(xi + i * 1024);
      mbar_wait(bar_xres, 0);
      wg_fence();
      HALF_STAGE(s, 9, 4);
      wg_commit();
      mbar_wait(bar_rx, 0);
      wg_fence();
      HALF_STAGE(s, 1, 5);
      wg_commit();
      bar_arrive(3 - wg, 256);
      STAMP(21);
#pragma unroll
      for (int i = LD2; i < 8; i++) v[i] = ld_b128(xi + i * 1024);
      mbar_wait(bar_xres, 0);
      wg_wait<0>();
      keep(s);
      mbar_arrive_pred(bar_ring + 16, lane0);
      PROF(10, ct == PT, 23); STAMP(4);
#pragma unroll
      for (int i = 0; i < 16; i += 2) ldmatrix4((trow ^ ((i & 7) << 4)) + (i >> 3) * 16384, xr[2 * i], xr[2 * i + 1], xr[2 * i + 2], xr[2 * i + 3]);
      uint32_t ga[16];
      uint4 bw[8];
#pragma unroll
      for (int i = 0; i < 8; i++) {
        if (!(i & 1)) {
          const uint4 t = lds4(par + PAR_SINK + i * 32 + tq * 16);
          ga[2 * i] = t.x; ga[2 * i + 1] = t.y; ga[2 * i + 2] = t.z; ga[2 * i + 3] = t.w;
        }
        bw[i] = lds4(par + PAR_T1 + i * 64 + tq * 16);
        if (!(g & 1)) { bw[i].x = 0x3f803f80u; bw[i].y = 0x3f803f80u; }
      }
      uint32_t pk[32];
      pack_p(s, pk);
      const uint32_t par2 = (~lds1(par + PAR_CONST + 12) & 1) << 16;
      {
        uint32_t n = 0, miss;
        do {
          miss = 0;
#pragma unroll
          for (int i = 0; i < 8; i++) miss |= v[i].x ^ par2;
          miss = __any_sync(0xffffffffu, miss & 0x10000u);
          if (miss) {
#pragma unroll
            for (int i = 0; i < 8; i++)
              asm volatile("{ .reg .pred p; .reg .b32 t; xor.b32 t, %0, %5; and.b32 t, t, 0x10000; setp.ne.u32 p, t, 0;\n"
                           "@p ld.relaxed.gpu.global.v4.u32 {%0, %1, %2, %3}, [%4]; }"
                           : "+r"(v[i].x), "+r"(v[i].y), "+r"(v[i].z), "+r"(v[i].w) : "l"(xi + i * 1024), "r"(par1) : "memory");
          }
          watchdog(n);
        } while (miss);
      }
      PROF(8, ct == PT, 22); STAMP(3);
      float ds[4] = {0.f, 0.f, 0.f, 0.f}, dl[4] = {0.f, 0.f, 0.f, 0.f}, q0[4] = {0.f, 0.f, 0.f, 0.f}, q1[4] = {0.f, 0.f, 0.f, 0.f};
#pragma unroll
      for (int i = 0; i < 8; i++) {
        const uint32_t u0 = hfma2(ga[2 * i], hadd2(pk[4 * i], v[i].x & ~0x10000u), xr[4 * i]);
        const uint32_t u1 = hfma2(ga[2 * i], hadd2(pk[4 * i + 1], v[i].y), xr[4 * i + 1]);
        const uint32_t u2 = hfma2(ga[2 * i + 1], hadd2(pk[4 * i + 2], v[i].z), xr[4 * i + 2]);
        const uint32_t u3 = hfma2(ga[2 * i + 1], hadd2(pk[4 * i + 3], v[i].w), xr[4 * i + 3]);
        xr[4 * i] = u0; xr[4 * i + 1] = u1; xr[4 * i + 2] = u2; xr[4 * i + 3] = u3;
        mma16816(ds, u0, u1, u2, u3, bw[i].x, bw[i].y);
        mma16816(dl, u0, u1, u2, u3, bw[i].z, bw[i].w);
        mma16816(q0, u0, u1, u2, u3, u0, u2);
        mma16816(q1, u0, u1, u2, u3, u1, u3);
      }
      const float sqa = (g & 1) ? q0[1] : q0[0], sqb = (g & 1) ? q1[3] : q1[2], dta = ds[1] + dl[1], dtb = ds[3] + dl[3];
      if (tq == (g >> 1)) {
        st_b128(sg + cj * 64, __float_as_uint(ds[0]), __float_as_uint(sqa), __float_as_uint(dta), tag);
        st_b128(sg + cj * 64 + 32, __float_as_uint(ds[2]), __float_as_uint(sqb), __float_as_uint(dtb), tag);
      }
#pragma unroll
      for (int k = 0; k < 4; k++) sv[k] = ld_b128(sp[k]);
      mbar_wait(bar_xres, 0);
      const float sqc = __shfl_sync(0xffffffffu, sqa, g * 4 + (g >> 1)), sqd = __shfl_sync(0xffffffffu, sqb, g * 4 + (g >> 1));
      own = (tq & 1) ? make_uint4(__float_as_uint(ds[2]), __float_as_uint(sqd), __float_as_uint(dtb), tag)
                     : make_uint4(__float_as_uint(ds[0]), __float_as_uint(sqc), __float_as_uint(dta), tag);
    }
    PROF(8, ct == PT, 29); STAMP(5);
    uint32_t mm, ih, il;
    float rbest;
    uint32_t wf[128];
    const uint32_t frow = (ln & 7) + (ln >> 4) * 8;
    const uint32_t wfo = base + (warp & 1) * 8192 + frow * 64 + ((((ln >> 3) & 1) ^ ((frow >> 1) & 3)) << 4);
#define LOAD_WF(m) _Pragma("unroll") for (int f = 0; f < 16; f++) {                                                   \
      const int r = ((f >> 1) * 4 + (m) * 2 + (f & 1)) * 4;                                                           \
      ldmatrix4t(((wfo + unit_of((m) ? FT_U : FT_G, warp >> 1)) ^ ((f & 1) * 32)) + (f >> 1) * 1024, wf[r], wf[r + 1], wf[r + 2], wf[r + 3]); \
    }
    bool early;
    {
#pragma unroll
      for (int i = 0; i < 16; i += 2) stmatrix4((trow ^ ((i & 7) << 4)) + (i >> 3) * 16384, xr[2 * i], xr[2 * i + 1], xr[2 * i + 2], xr[2 * i + 3]);
      const uint4 cst = lds4(par + PAR_CONST);
      const float A1 = __uint_as_float(cst.x), A2 = __uint_as_float(cst.z);
      uint32_t n = 0;
      early = false;
#pragma unroll 1
      while (true) {
        if (!early && (b >= NFFN || __all_sync(0xffffffffu, mbar_test(bar_box + (warp >> 1) * 8, 0)))) {
          early = true;
          LOAD_WF(0);
          __syncwarp();
          mbar_arrive_pred(bar_gate, lane0);
        }
        uint32_t miss;
        asm volatile("{ .reg .pred p0, p1, p2, p3; .reg .b64 u, v; .reg .b128 w;\n"
                     "setp.ge.u32 p0, %22, 2; setp.ne.and.u32 p0, %4, %21, p0; setp.ne.u32 p1, %8, %21; setp.ne.u32 p2, %12, %21; setp.ne.u32 p3, %16, %21;\n"
                     "@p0 ld.relaxed.gpu.global.v4.u32 {%1, %2, %3, %4}, [%17];\n"
                     "@p1 ld.relaxed.gpu.global.v4.u32 {%5, %6, %7, %8}, [%18];\n"
                     "@p2 ld.relaxed.gpu.global.v4.u32 {%9, %10, %11, %12}, [%19];\n"
                     "@p3 ld.relaxed.gpu.global.v4.u32 {%13, %14, %15, %16}, [%20];\n"
                     "or.pred p0, p0, p1; or.pred p2, p2, p3; or.pred p0, p0, p2; vote.sync.any.pred p0, p0, 0xffffffff; selp.u32 %0, 1, 0, p0; }"
                     : "=r"(miss), "+r"(sv[0].x), "+r"(sv[0].y), "+r"(sv[0].z), "+r"(sv[0].w), "+r"(sv[1].x), "+r"(sv[1].y), "+r"(sv[1].z), "+r"(sv[1].w),
                       "+r"(sv[2].x), "+r"(sv[2].y), "+r"(sv[2].z), "+r"(sv[2].w), "+r"(sv[3].x), "+r"(sv[3].y), "+r"(sv[3].z), "+r"(sv[3].w)
                     : "l"(sp[0]), "l"(sp[1]), "l"(sp[2]), "l"(sp[3]), "r"(tag), "r"(tq) : "memory");
        if (!miss) break;
        watchdog(n);
      }
      const uint4 v0 = tq < 2 ? own : sv[0], v1 = sv[1], v2 = sv[2], v3 = sv[3];
      PROF(8, ct == PT, 30); STAMP(6);
      float su = (__uint_as_float(v0.x) + __uint_as_float(v1.x)) + (__uint_as_float(v2.x) + __uint_as_float(v3.x));
      float sq = (__uint_as_float(v0.y) + __uint_as_float(v1.y)) + (__uint_as_float(v2.y) + __uint_as_float(v3.y));
      float dt = (__uint_as_float(v0.z) + __uint_as_float(v1.z)) + (__uint_as_float(v2.z) + __uint_as_float(v3.z));
      su += __shfl_xor_sync(0xffffffffu, su, 2); sq += __shfl_xor_sync(0xffffffffu, sq, 2); dt += __shfl_xor_sync(0xffffffffu, dt, 2);
      const float m = su * (1.f / DM);
      float mb, sd;
      ln_scalars(m, fmaxf(sq * (1.f / DM) - m * m, 0.f), mb, sd);
      const float inv = rcp(sd);
      rbest = (dt - mb * A1) * inv + A2;
      mm = pack_bf(mb, mb);
      ih = pack_bf(inv, inv);
      const float lo = inv - bf_lo(ih);
      il = pack_bf(lo, lo);
    }
    int ibest;
    {
      const uint32_t bits = __float_as_uint(rbest);
      const uint32_t key = (((int)bits < 0 ? ~bits : bits | 0x80000000u) & ~0x1ffu) | ((127 - lrow0 - (tq & 1) * 8) << 2) | tag;
      sts1(par + PAR_RED + warp * 4, __reduce_max_sync(0xffffffffu, key));
      PROF(8, ct == PT, 38); STAMP(7);
      bar_sync(1, 256);
      const uint4 ka = lds4(par + PAR_RED), kb = lds4(par + PAR_RED + 16);
      const uint32_t k2 = max(max(max(ka.x, ka.y), max(ka.z, ka.w)), max(max(kb.x, kb.y), max(kb.z, kb.w)));
      if (ct < CR && cj == 0) st_relaxed(g_cand + ct * 512 + rb * CS, k2);
      ibest = 127 - ((k2 >> 2) & 127);
    }
    PROF(8, ct == PT, 39); STAMP(8);
    if ((ibest >> 4) == warp) {
      const int src = (ibest & 7) * 4 + ((ibest >> 3) & 1), ch = g * 2;
      const uint32_t cm = __shfl_sync(0xffffffffu, mm, src), ch_ = __shfl_sync(0xffffffffu, ih, src), cl = __shfl_sync(0xffffffffu, il, src);
      const uint32_t xa = res + (ch >> 3) * 16384 + ibest * 128 + (((ch & 7) ^ (ibest & 7)) << 4) + tq * 4;
      const uint32_t x0 = lds1(xa), x1 = lds1(xa ^ 16);
      const uint2 p0 = lds2(par + PAR_T2 + ch * 64 + tq * 16), p1 = lds2(par + PAR_T2 + ch * 64 + 64 + tq * 16);
      uint32_t* dst = g_row + rb * 2 * DM + cj * 128 + ln * 4;
      st_pairs(dst, ln_mod(x0, cm, ch_, cl, p0.x, p0.y), ln_mod(x1, cm, ch_, cl, p1.x, p1.y), tag);
      st_pairs(dst + DM, x0, x1, tag);
      __syncwarp();
    }
    PROF(8, ct == PT, 37); STAMP(9);
    uint32_t wd[64];
    const uint32_t wda = base + unit_of(FT_D, warp >> 1) + (warp & 1) * 8192 + frow * 128 + ((((ln >> 3) & 1) ^ (ln & 7)) << 4);
#define LOAD_WD(f) ldmatrix4t((wda ^ ((((f) >> 1) & 3) * 32)) + ((f) >> 3) * 4096 + ((f) & 1) * 2048, wd[4 * (f)], wd[4 * (f) + 1], wd[4 * (f) + 2], wd[4 * (f) + 3])
    if (!early) {
      if (b < NFFN) mbar_wait(bar_box + (warp >> 1) * 8, 0);
      LOAD_WF(0);
      __syncwarp();
      mbar_arrive_pred(bar_gate, lane0);
    }
    if (b < NFFN) {
      const uint32_t own = base + unit_of(FT_G, warp >> 1) + (warp & 1) * 8192;
      mbar_wait(bar_box + (4 + (warp >> 1)) * 8, 0);
      LOAD_WF(1);
      uint32_t* const ydst = ypart_slot(b, warp * 16 + (tq & 1) * 8 + g);
      PROF(8, ct == PT, 31); STAMP(10);
      bool wdok;
      {
        uint32_t n = 0;
        while (!(wdok = __all_sync(0xffffffffu, mbar_test(bar_box + (8 + (warp >> 1)) * 8, 0))) && !__all_sync(0xffffffffu, mbar_test(bar_sel, 0))) watchdog(n);
      }
      if (wdok) {
#pragma unroll
        for (int f = 0; f < 16; f++) LOAD_WD(f);
      }
      STAMP(11);
      mbar_wait(bar_sel, 0);
      PROF(8, ct == PT, 33); STAMP(12);
      float d[8][4];
#pragma unroll
      for (int i = 0; i < 4; i++) { d[i][0] = 0.f; d[i][1] = 0.f; d[i][2] = 0.f; d[i][3] = 0.f; }
#pragma unroll
      for (int ks = 0; ks < 8; ks++) {
        const uint2 hb = lds2(own + 256 + ks * 32 + tq * 8);
#pragma unroll
        for (int mt = 0; mt < 4; mt++) {
          const int r = ks * 16 + mt * 4;
          mma16816(d[mt], wf[r], wf[r + 1], wf[r + 2], wf[r + 3], hb.x, hb.y);
        }
      }
      sts2(own + (tq * 8 + g) * 8, __float_as_uint((tq & 2) ? ((tq & 1) ? d[1][2] : d[1][0]) : ((tq & 1) ? d[0][2] : d[0][0])),
           __float_as_uint((tq & 2) ? ((tq & 1) ? d[3][2] : d[3][0]) : ((tq & 1) ? d[2][2] : d[2][0])));
      bar_sync(1, 256);
      uint32_t ab[4];
      {
        float G = 0.f, U = 0.f;
        uint2 pv[8];
#pragma unroll
        for (int w8 = 0; w8 < 8; w8++) pv[w8] = lds2(base + ln * 8 + ((FT_G >> (w8 >> 1) * 4) & 15) * UNIT + (w8 & 1) * 8192);
#pragma unroll
        for (int w8 = 0; w8 < 8; w8 += 2) {
          G += __uint_as_float(pv[w8].x) + __uint_as_float(pv[w8 + 1].x);
          U += __uint_as_float(pv[w8].y) + __uint_as_float(pv[w8 + 1].y);
        }
        const float act = rbf(silu_f(rbf(G))) * rbf(U);
        const uint32_t pk = pack_bf(act, __shfl_down_sync(0xffffffffu, act, 1));
#pragma unroll
        for (int i = 0; i < 4; i++) ab[i] = __shfl_sync(0xffffffffu, pk, i * 8 + tq * 2);
      }
      if (!wdok) {
        mbar_wait(bar_box + (8 + (warp >> 1)) * 8, 0);
#pragma unroll
        for (int f = 0; f < 16; f++) LOAD_WD(f);
      }
      PROF(8, ct == PT, 34); STAMP(13);
#pragma unroll
      for (int mt = 0; mt < 8; mt++) {
        d[mt][0] = 0.f; d[mt][1] = 0.f; d[mt][2] = 0.f; d[mt][3] = 0.f;
        mma16816(d[mt], wd[mt * 8], wd[mt * 8 + 1], wd[mt * 8 + 2], wd[mt * 8 + 3], ab[0], ab[1]);
        mma16816(d[mt], wd[mt * 8 + 4], wd[mt * 8 + 5], wd[mt * 8 + 6], wd[mt * 8 + 7], ab[2], ab[3]);
      }
      uint32_t yw[4];
#pragma unroll
      for (int i = 0; i < 4; i++) yw[i] = (tq & 1) ? pack_bf(d[2 * i][2], d[2 * i + 1][2]) : pack_bf(d[2 * i][0], d[2 * i + 1][0]);
      if (tq < 2) st_b128(ydst, (yw[0] & ~1u) | (tag & 1), (yw[1] & ~1u) | (tag >> 1), yw[2], yw[3]);
      PROF(8, ct == PT, 35); STAMP(14);
    }
    mbar_wait(bar_sel, 0);
    mbar_arrive_pred(bar_win, ct == 0);
    const int iwin = lds1(par + PAR_CONST + 60) & 0x7ff;
    const bool cand = (iwin >> 4) == rb * 8 + warp;
    {
      const uint32_t mm0 = __shfl_sync(0xffffffffu, mm, ln & ~1), mm1 = __shfl_sync(0xffffffffu, mm, ln | 1);
      const uint32_t ih0 = __shfl_sync(0xffffffffu, ih, ln & ~1), ih1 = __shfl_sync(0xffffffffu, ih, ln | 1);
      const uint32_t il0 = __shfl_sync(0xffffffffu, il, ln & ~1), il1 = __shfl_sync(0xffffffffu, il, ln | 1);
#pragma unroll 1
      for (int hf = 0; hf < 2; hf++) {
        uint32_t x[16];
#pragma unroll
        for (int i = 0; i < 8; i += 2) ldmatrix4((trow ^ (i << 4)) + hf * 16384, x[2 * i], x[2 * i + 1], x[2 * i + 2], x[2 * i + 3]);
#pragma unroll
        for (int i = 0; i < 8; i++) {
          const uint4 pv = lds4(par + PAR_T2 + (hf * 8 + i) * 64 + tq * 16);
          x[2 * i] = hfma2(hfma2(ln_norm(x[2 * i], mm0, ih0, il0), pv.x, pv.y), pv.z, x[2 * i]);
          x[2 * i + 1] = hfma2(hfma2(ln_norm(x[2 * i + 1], mm1, ih1, il1), pv.x, pv.y), pv.z, x[2 * i + 1]);
        }
#pragma unroll
        for (int i = 0; i < 8; i += 2) stmatrix4((trow ^ (i << 4)) + hf * 16384, x[2 * i], x[2 * i + 1], x[2 * i + 2], x[2 * i + 3]);
        if (!cand) fence_async_smem();
        __syncwarp();
        if (!cand && elect_one()) {
          tma2d_store(&maps.out, res + hf * 16384 + warp * 2048, cj * 128 + hf * 64, rb * 128 + warp * 16);
          asm volatile("cp.async.bulk.commit_group;" ::: "memory");
        }
      }
    }
    if (cand) {
      const int wrow0 = warp * 16;
#pragma unroll 2
      for (int p = 0; p < 8; p++) {
        const int row = 2 * p + (ln >> 4), ch = ln & 15;
        const uint4 v = lds4(res + (ch >> 3) * 16384 + (wrow0 + row) * 128 + (((ch & 7) ^ (row & 7)) << 4));
        if (rb * 128 + wrow0 + row != iwin) *reinterpret_cast<uint4*>(P.out + (size_t)(rb * 128 + wrow0 + row) * DM + cj * 128 + ch * 8) = v;
      }
    }
    asm volatile("cp.async.bulk.wait_group.read 0;" ::: "memory");
    PROF(8, ct == PT, 11); STAMP(15);
    cluster_wait();
  }
}

typedef CUresult (*EncodeFn)(CUtensorMap*, CUtensorMapDataType, cuuint32_t, void*, const cuuint64_t*, const cuuint64_t*,
                             const cuuint32_t*, const cuuint32_t*, CUtensorMapInterleave, CUtensorMapSwizzle,
                             CUtensorMapL2promotion, CUtensorMapFloatOOBfill);

void map2d(EncodeFn enc, CUtensorMap* m, const void* p, uint64_t rows, uint64_t cols, uint32_t brows) {
  cuuint64_t dims[2] = {cols, rows}, strides[1] = {cols * 2};
  cuuint32_t box[2] = {64, brows}, es[2] = {1, 1};
  enc(m, CU_TENSOR_MAP_DATA_TYPE_BFLOAT16, 2, const_cast<void*>(p), dims, strides, box, es, CU_TENSOR_MAP_INTERLEAVE_NONE,
      CU_TENSOR_MAP_SWIZZLE_128B, CU_TENSOR_MAP_L2_PROMOTION_L2_256B, CU_TENSOR_MAP_FLOAT_OOB_FILL_NONE);
}
void map2d_narrow(EncodeFn enc, CUtensorMap* m, const void* p, uint64_t rows, uint64_t cols, uint32_t brows) {
  cuuint64_t dims[2] = {cols, rows}, strides[1] = {cols * 2};
  cuuint32_t box[2] = {32, brows}, es[2] = {1, 1};
  enc(m, CU_TENSOR_MAP_DATA_TYPE_BFLOAT16, 2, const_cast<void*>(p), dims, strides, box, es, CU_TENSOR_MAP_INTERLEAVE_NONE,
      CU_TENSOR_MAP_SWIZZLE_64B, CU_TENSOR_MAP_L2_PROMOTION_L2_64B, CU_TENSOR_MAP_FLOAT_OOB_FILL_NONE);
}
void map3d(EncodeFn enc, CUtensorMap* m, const void* p, uint64_t rows, uint64_t cols, uint32_t brows, uint32_t nch) {
  cuuint64_t dims[3] = {64, rows, cols / 64}, strides[2] = {cols * 2, 128};
  cuuint32_t box[3] = {64, brows, nch}, es[3] = {1, 1, 1};
  enc(m, CU_TENSOR_MAP_DATA_TYPE_BFLOAT16, 3, const_cast<void*>(p), dims, strides, box, es, CU_TENSOR_MAP_INTERLEAVE_NONE,
      CU_TENSOR_MAP_SWIZZLE_128B, CU_TENSOR_MAP_L2_PROMOTION_L2_256B, CU_TENSOR_MAP_FLOAT_OOB_FILL_NONE);
}

}

extern "C" void kernel_launch(void* const* d_in, const int* in_sizes, int n_in, void* d_out, int out_size) {
  (void)in_sizes; (void)n_in; (void)out_size;
  static EncodeFn enc = nullptr;
  if (!enc) {
    void* fn = nullptr;
    cudaDriverEntryPointQueryResult st;
    cudaGetDriverEntryPoint("cuTensorMapEncodeTiled", &fn, cudaEnableDefault, &st);
    enc = (EncodeFn)fn;
    cudaFuncSetAttribute(fused_kernel, cudaFuncAttributeMaxDynamicSharedMemorySize, SMEM_BYTES);
  }
  Maps maps;
  map2d(enc, &maps.x, d_in[0], SEQ, DM, 128);
  map2d(enc, &maps.out, d_out, SEQ, DM, 16);
  map3d(enc, &maps.wq, d_in[3], DM, NQ, 64, 2);
  map3d(enc, &maps.k, d_in[1], 4 * SK, 128, 128, 1);
  map3d(enc, &maps.v, d_in[2], 4 * SK, 128, 128, 1);
  map3d(enc, &maps.wo, d_in[4], NQ, DM, 64, 2);
  map2d_narrow(enc, &maps.wg, d_in[7], DM, FF, 256);
  map2d_narrow(enc, &maps.wu, d_in[8], DM, FF, 256);
  map3d(enc, &maps.wd, d_in[9], FF, DM, 32, 4);
  map2d_narrow(enc, &maps.wm, d_in[11], DM, NMOD, 256);
  Ptrs p;
  p.x = (const __nv_bfloat16*)d_in[0];
  p.w_r = (const __nv_bfloat16*)d_in[6];
  p.w_gate = (const __nv_bfloat16*)d_in[7];
  p.w_up = (const __nv_bfloat16*)d_in[8];
  p.w_down = (const __nv_bfloat16*)d_in[9];
  p.c = (const __nv_bfloat16*)d_in[10];
  p.w_mod = (const __nv_bfloat16*)d_in[11];
  p.out = (__nv_bfloat16*)d_out;
  fused_kernel<<<NMAIN + NHELP, 384, SMEM_BYTES>>>(p, maps);
}
```

```cpp
#include <cuda_runtime.h>
#include <cuda_bf16.h>
#include <cuda.h>
#include <stdint.h>
#include <type_traits>

#define HD 2
#define HDX 2
#define NRS 8
#define OSL 900
#define OSL2 400
#define RSL 40
#define BIAS 102.f
#define VREL 5
#define OPS 8192
#define ODS1 5
#define ODS 7
#define PG0 15
#define WB 2
#define WN 20
#define HU 32
#define RES0 17
#define RES1 20
#define GOST 20
#define NS1 5
#define LD2 4
#define FPACE0 2
#define FPACE 3
#define CR 8
#define CS 8

namespace {

constexpr int SEQ = 2048, DM = 1024, NQ = 4096, SK = 2048, WIN = 512, FF = 3584, NMOD = 6144;
constexpr int NMAIN = 128, NHELP = 4, NFFN = 112;
constexpr int NSLOT = 4, SLOT_BYTES = 32768, UNIT = 16384, GST_BYTES = 3 * UNIT;
constexpr uint32_t XT1 = 0xDCBA, XT2 = 0x9687;
constexpr uint32_t WT0 = 0xA741, WT1 = 0x7420, WT2 = 0x4A20;
constexpr uint32_t AT0 = WT1, AT1 = WT2;
constexpr uint32_t QT = 0xDC9696DC;
constexpr int OFF_STAGE = 12 * UNIT;
constexpr uint32_t FT_G = 0x07B3, FT_U = 0xA628, FT_D = 0x5149;
constexpr int OFF_RES = 12 * UNIT;
constexpr int OFF_PAR = 14 * UNIT;
constexpr int OFF_BAR = OFF_PAR + 2528;
constexpr int SMEM_BYTES = OFF_BAR + 544;
static_assert(SMEM_BYTES <= 232448, "smem");

constexpr int PAR_T1 = 0;
constexpr int PAR_T2 = 512;
constexpr int PAR_CONST = 1536;
constexpr int PAR_RED = 1600;
constexpr int PAR_SINK = 2176;

struct Maps {
  CUtensorMap x, wq, k, v, wo, wg, wu, wd, wm, out;
};
struct Ptrs {
  const __nv_bfloat16 *x, *c, *w_r, *w_mod, *w_gate, *w_up, *w_down;
  __nv_bfloat16* out;
};

__device__ __align__(1024) uint8_t g_act[16 * 80 * UNIT];
__device__ __align__(128) uint32_t g_mod[NMOD];
__device__ __align__(128) uint32_t g_modp[2 * 2 * DM];
__device__ __align__(128) uint32_t g_ln1[SEQ * 4];
__device__ __align__(128) uint32_t g_cnt_h[16 * 32];
__device__ __align__(128) uint32_t g_cnt_o[128 * 32];
__device__ __align__(128) uint32_t g_xch[NMAIN * 8 * 256 * 4];
__device__ __align__(128) uint32_t g_stats[8 * SEQ * 4];
__device__ __align__(128) uint32_t g_cand[CR * 512];
__device__ __align__(128) uint32_t g_row[16 * 2 * DM];
__device__ __align__(128) uint32_t g_ypart[NMAIN * NFFN * 4];
__device__ __forceinline__ uint32_t* ypart_slot(int writer, int reader) { return g_ypart + (writer * NMAIN + reader) * 4; }
__device__ uint32_t g_epoch;

__device__ __forceinline__ uint32_t fresh_lane() { uint32_t l; asm volatile("mov.u32 %0, %%laneid;" : "=r"(l)); return l; }
__device__ __forceinline__ uint32_t frag_offset(int warp) {
  const uint32_t l = fresh_lane();
  return ((warp & 3) * 16 + (l & 15)) * 128 + (((l >> 4) ^ (l & 7)) << 4);
}
__device__ __forceinline__ bool elect_one() {
  uint32_t p;
  asm volatile("{ .reg .pred q; elect.sync _|q, 0xffffffff; selp.u32 %0, 1, 0, q; }" : "=r"(p));
  return p;
}
__device__ __forceinline__ uint32_t smem_u32(const void* p) { return (uint32_t)__cvta_generic_to_shared(p); }
__device__ __forceinline__ void mbar_init(uint32_t bar, uint32_t cnt) {
  asm volatile("mbarrier.init.shared::cta.b64 [%0], %1;" ::"r"(bar), "r"(cnt) : "memory");
}
__device__ __forceinline__ void mbar_expect_tx(uint32_t bar, uint32_t bytes) {
  asm volatile("mbarrier.arrive.expect_tx.shared::cta.b64 _, [%0], %1;" ::"r"(bar), "r"(bytes) : "memory");
}
__device__ __forceinline__ void mbar_arrive(uint32_t bar) {
  asm volatile("mbarrier.arrive.shared::cta.b64 _, [%0];" ::"r"(bar) : "memory");
}
__device__ __forceinline__ void mbar_arrive_pred(uint32_t bar, bool p) {
  asm volatile("{ .reg .pred p; setp.ne.b32 p, %1, 0; @p mbarrier.arrive.shared::cta.b64 _, [%0]; }" ::"r"(bar), "r"((int)p) : "memory");
}
__device__ __forceinline__ void mbar_arrive_cl(uint32_t bar, uint32_t off, bool p = true) {
  asm volatile("{ .reg .pred p, q; .reg .b32 a; setp.ne.b32 q, %2, 0; setp.ne.and.b32 p, %0, 0, q; add.u32 a, %0, %1; @p mbarrier.arrive.shared::cluster.b64 _, [a]; }"
               ::"r"(bar), "r"(off), "r"((int)p) : "memory");
}
__device__ __forceinline__ uint32_t mapa(uint32_t addr, uint32_t cta) {
  uint32_t r; asm("mapa.shared::cluster.u32 %0, %1, %2;" : "=r"(r) : "r"(addr), "r"(cta)); return r;
}
__device__ __forceinline__ void cluster_arrive() { asm volatile("barrier.cluster.arrive.relaxed.aligned;" ::: "memory"); }
__device__ __forceinline__ void cluster_wait() { asm volatile("barrier.cluster.wait.aligned;" ::: "memory"); }
__device__ __forceinline__ void watchdog(uint32_t& n) {
}
__device__ __forceinline__ void mbar_wait(uint32_t bar, uint32_t parity) {
  asm volatile("{\n.reg .pred p;\nWAIT_%=:\nmbarrier.try_wait.parity.shared::cta.b64 p, [%0], %1;\n@!p bra WAIT_%=;\n}" ::"r"(bar), "r"(parity) : "memory");
}
__device__ __forceinline__ bool mbar_test(uint32_t bar, uint32_t parity) {
  uint32_t ok;
  asm volatile("{\n.reg .pred p;\nmbarrier.test_wait.parity.shared::cta.b64 p, [%1], %2;\nselp.u32 %0, 1, 0, p;\n}" : "=r"(ok) : "r"(bar), "r"(parity) : "memory");
  return ok;
}
__device__ __forceinline__ uint64_t l2_stream() {
  uint64_t f; asm("createpolicy.fractional.L2::evict_first.b64 %0, 1.0;" : "=l"(f)); return f;
}
__device__ __forceinline__ uint64_t l2_normal() {
  uint64_t f; asm("createpolicy.fractional.L2::evict_normal.b64 %0, 1.0;" : "=l"(f)); return f;
}
__device__ __forceinline__ void tma2d(uint32_t dst, const CUtensorMap* m, int c0, int c1, uint32_t bar) {
  asm volatile("cp.async.bulk.tensor.2d.shared::cluster.global.mbarrier::complete_tx::bytes.L2::cache_hint [%0], [%1, {%3, %4}], [%2], %5;"
               ::"r"(dst), "l"(m), "r"(bar), "r"(c0), "r"(c1), "l"(l2_stream()) : "memory");
}
__device__ __forceinline__ void bulk_load(uint32_t dst, const void* src, uint32_t bytes, uint32_t bar) {
  asm volatile("cp.async.bulk.shared::cluster.global.mbarrier::complete_tx::bytes [%0], [%1], %2, [%3];" ::"r"(dst), "l"(src), "r"(bytes), "r"(bar) : "memory");
}
__device__ __forceinline__ void bulk_load_stream(uint32_t dst, const void* src, uint32_t bytes, uint32_t bar, uint64_t pol = l2_stream()) {
  asm volatile("cp.async.bulk.shared::cluster.global.mbarrier::complete_tx::bytes.L2::cache_hint [%0], [%1], %2, [%3], %4;"
               ::"r"(dst), "l"(src), "r"(bytes), "r"(bar), "l"(pol) : "memory");
}
__device__ __forceinline__ void tma2d_store(const CUtensorMap* m, uint32_t src, int c0, int c1) {
  asm volatile("cp.async.bulk.tensor.2d.global.shared::cta.bulk_group [%0, {%2, %3}], [%1];" ::"l"(m), "r"(src), "r"(c0), "r"(c1) : "memory");
}
__device__ __forceinline__ void bulk_store(void* dst, uint32_t src, uint32_t bytes) {
  asm volatile("cp.async.bulk.global.shared::cta.bulk_group [%0], [%1], %2;" ::"l"(dst), "r"(src), "r"(bytes) : "memory");
}
__device__ __forceinline__ int slice_of(int i) { return (i & 8) + ((0x76531420u >> (i & 7) * 4) & 7); }
__device__ __forceinline__ uint32_t unit_of(uint32_t table, uint32_t i) { return ((table >> (i * 4)) & 15) * UNIT; }
__device__ __forceinline__ void tma3d(uint32_t dst, const CUtensorMap* m, int c0, int c1, int c2, uint32_t bar) {
  asm volatile("cp.async.bulk.tensor.3d.shared::cluster.global.mbarrier::complete_tx::bytes.L2::cache_hint [%0], [%1, {%3, %4, %5}], [%2], %6;"
               ::"r"(dst), "l"(m), "r"(bar), "r"(c0), "r"(c1), "r"(c2), "l"(l2_stream()) : "memory");
}
template <bool STREAM>
__device__ __forceinline__ void tma3d_mc(uint32_t dst, const CUtensorMap* m, int c0, int c1, int c2, uint32_t bar) {
  if (STREAM)
    asm volatile("cp.async.bulk.tensor.3d.shared::cluster.global.mbarrier::complete_tx::bytes.multicast::cluster.L2::cache_hint [%0], [%1, {%3, %4, %5}], [%2], %6, %7;"
                 ::"r"(dst), "l"(m), "r"(bar), "r"(c0), "r"(c1), "r"(c2), "h"((uint16_t)3), "l"(l2_stream()) : "memory");
  else
    asm volatile("cp.async.bulk.tensor.3d.shared::cluster.global.mbarrier::complete_tx::bytes.multicast::cluster [%0], [%1, {%3, %4, %5}], [%2], %6;"
                 ::"r"(dst), "l"(m), "r"(bar), "r"(c0), "r"(c1), "r"(c2), "h"((uint16_t)3) : "memory");
}
__device__ __forceinline__ void prefetch_map(const CUtensorMap* m) {
  asm volatile("prefetch.tensormap [%0];" ::"l"(m) : "memory");
}
__device__ __forceinline__ void fence_async() { asm volatile("fence.proxy.async.global;" ::: "memory"); }
__device__ __forceinline__ void fence_async_smem() { asm volatile("fence.proxy.async.shared::cta;" ::: "memory"); }
__device__ __forceinline__ void bar_sync(int id, int n) { asm volatile("bar.sync %0, %1;" ::"r"(id), "r"(n) : "memory"); }
__device__ __forceinline__ void bar_arrive(int id, int n) { asm volatile("bar.arrive %0, %1;" ::"r"(id), "r"(n) : "memory"); }
__device__ __forceinline__ void wg_fence() { asm volatile("wgmma.fence.sync.aligned;" ::: "memory"); }
__device__ __forceinline__ void wg_commit() { asm volatile("wgmma.commit_group.sync.aligned;" ::: "memory"); }
template <int N> __device__ __forceinline__ void wg_wait() { asm volatile("wgmma.wait_group.sync.aligned %0;" ::"n"(N) : "memory"); }
__device__ __forceinline__ uint64_t make_desc(uint32_t addr, uint32_t lbo, uint32_t sbo) {
  return (uint64_t)((addr & 0x3FFFF) >> 4) | ((uint64_t)(lbo >> 4) << 16) | ((uint64_t)(sbo >> 4) << 32) | (1ull << 62);
}
__device__ __forceinline__ uint32_t ld_relaxed(const uint32_t* p) {
  uint32_t v; asm volatile("ld.relaxed.gpu.global.u32 %0, [%1];" : "=r"(v) : "l"(p) : "memory"); return v;
}
__device__ __forceinline__ uint32_t ld_acquire(const uint32_t* p) {
  uint32_t v; asm volatile("ld.acquire.gpu.global.u32 %0, [%1];" : "=r"(v) : "l"(p) : "memory"); return v;
}
__device__ __forceinline__ uint4 ld_relaxed4(const uint32_t* p) {
  uint4 v; asm volatile("ld.relaxed.gpu.global.v4.u32 {%0,%1,%2,%3}, [%4];" : "=r"(v.x), "=r"(v.y), "=r"(v.z), "=r"(v.w) : "l"(p) : "memory"); return v;
}
__device__ __forceinline__ void st_relaxed(uint32_t* p, uint32_t v) {
  asm volatile("st.relaxed.gpu.global.u32 [%0], %1;" ::"l"(p), "r"(v) : "memory");
}
__device__ __forceinline__ void st_relaxed4(uint32_t* p, uint32_t a, uint32_t b, uint32_t c, uint32_t d) {
  asm volatile("st.relaxed.gpu.global.v4.u32 [%0], {%1,%2,%3,%4};" ::"l"(p), "r"(a), "r"(b), "r"(c), "r"(d) : "memory");
}
__device__ __forceinline__ void st_b128(uint32_t* p, uint32_t a, uint32_t b, uint32_t c, uint32_t d) {
  asm volatile("{ .reg .b64 u, v; .reg .b128 w; mov.b64 u, {%1, %2}; mov.b64 v, {%3, %4}; mov.b128 w, {u, v}; st.relaxed.gpu.global.b128 [%0], w; }"
               ::"l"(p), "r"(a), "r"(b), "r"(c), "r"(d) : "memory");
}
__device__ __forceinline__ uint4 ld_b128(const uint32_t* p) {
  uint4 r;
  asm volatile("{ .reg .b64 u, v; .reg .b128 w; ld.relaxed.gpu.global.b128 w, [%4]; mov.b128 {u, v}, w; mov.b64 {%0, %1}, u; mov.b64 {%2, %3}, v; }"
               : "=r"(r.x), "=r"(r.y), "=r"(r.z), "=r"(r.w) : "l"(p) : "memory");
  return r;
}
__device__ __forceinline__ void st_pairs(uint32_t* p, uint32_t a, uint32_t b, uint32_t tag) {
  asm volatile("{ .reg .b64 u, v; mov.b64 u, {%1, %3}; mov.b64 v, {%2, %3}; st.relaxed.gpu.global.v2.b64 [%0], {u, v}; }"
               ::"l"(p), "r"(a), "r"(b), "r"(tag) : "memory");
}
__device__ __forceinline__ uint4 ld_pairs(const uint32_t* p) {
  uint4 v;
  asm volatile("{ .reg .b64 u, v; ld.relaxed.gpu.global.v2.b64 {u, v}, [%4]; mov.b64 {%0, %1}, u; mov.b64 {%2, %3}, v; }"
               : "=r"(v.x), "=r"(v.y), "=r"(v.z), "=r"(v.w) : "l"(p) : "memory");
  return v;
}
__device__ __forceinline__ uint2 ld_pair(const uint32_t* p) {
  uint2 v;
  asm volatile("{ .reg .b64 u; ld.relaxed.gpu.global.b64 u, [%2]; mov.b64 {%0, %1}, u; }" : "=r"(v.x), "=r"(v.y) : "l"(p) : "memory");
  return v;
}
__device__ __forceinline__ void red_release(uint32_t* p, uint32_t v) {
  asm volatile("red.release.gpu.global.add.u32 [%0], %1;" ::"l"(p), "r"(v) : "memory");
}
__device__ __forceinline__ uint32_t ldg_nc1(const void* p) {
  uint32_t v;
  asm volatile("ld.global.nc.u32 %0, [%1];" : "=r"(v) : "l"(p));
  return v;
}
__device__ __forceinline__ uint4 ldg_nc4(const void* p) {
  uint4 v; asm volatile("ld.global.nc.L1::no_allocate.v4.u32 {%0,%1,%2,%3}, [%4];" : "=r"(v.x), "=r"(v.y), "=r"(v.z), "=r"(v.w) : "l"(p)); return v;
}
__device__ __forceinline__ uint4 ldg_stream4(const void* p) {
  uint4 v;
  asm volatile("ld.global.nc.L1::no_allocate.L2::cache_hint.v4.u32 {%0,%1,%2,%3}, [%4], %5;" : "=r"(v.x), "=r"(v.y), "=r"(v.z), "=r"(v.w) : "l"(p), "l"(l2_stream()));
  return v;
}
__device__ __forceinline__ void stg4(void* p, uint4 v) {
  asm volatile("st.global.v4.u32 [%0], {%1,%2,%3,%4};" ::"l"(p), "r"(v.x), "r"(v.y), "r"(v.z), "r"(v.w) : "memory");
}
__device__ __forceinline__ void wait_counter(const uint32_t* p, uint32_t target) {
  uint32_t n = 0;
  while (__any_sync(0xffffffffu, (int)(ld_acquire(p) - target) < 0)) { watchdog(n); }
}
__device__ __forceinline__ uint32_t tagf(float v, uint32_t tag) { return (__float_as_uint(v) & ~3u) | tag; }
__device__ __forceinline__ bool tag_ok(uint4 v, uint32_t tag) { return (((v.x ^ tag) | (v.y ^ tag) | (v.z ^ tag) | (v.w ^ tag)) & 3u) == 0; }
__device__ __forceinline__ float untag_sum(uint32_t a, uint32_t b) { return __uint_as_float(a & ~3u) + __uint_as_float(b & ~3u); }
__device__ __forceinline__ uint4 poll4(const uint32_t* p, uint32_t tag) {
  uint4 v = ld_relaxed4(p);
  uint32_t n = 0;
  while (!__all_sync(0xffffffffu, tag_ok(v, tag))) { v = ld_relaxed4(p); watchdog(n); }
  return v;
}
__device__ __forceinline__ float bf_lo(uint32_t v) { return __uint_as_float(v << 16); }
__device__ __forceinline__ float bf_hi(uint32_t v) { return __uint_as_float(v & 0xffff0000u); }
__device__ __forceinline__ uint32_t pack_bf(float lo, float hi) {
  uint32_t r; asm("cvt.rn.bf16x2.f32 %0, %1, %2;" : "=r"(r) : "f"(hi), "f"(lo)); return r;
}
__device__ __forceinline__ float rbf(float v) { return __uint_as_float(pack_bf(0.f, v) & 0xffff0000u); }
__device__ __forceinline__ uint32_t hmul2(uint32_t a, uint32_t b) {
  uint32_t r; asm("mul.rn.bf16x2 %0, %1, %2;" : "=r"(r) : "r"(a), "r"(b)); return r;
}
__device__ __forceinline__ uint32_t hadd2(uint32_t a, uint32_t b) {
  uint32_t r; asm("add.rn.bf16x2 %0, %1, %2;" : "=r"(r) : "r"(a), "r"(b)); return r;
}
__device__ __forceinline__ uint32_t hsub2(uint32_t a, uint32_t b) {
  uint32_t r; asm("sub.rn.bf16x2 %0, %1, %2;" : "=r"(r) : "r"(a), "r"(b)); return r;
}
__device__ __forceinline__ float rcp(float x) { float r; asm("rcp.approx.ftz.f32 %0, %1;" : "=f"(r) : "f"(x)); return r; }
__device__ __forceinline__ float ex2(float x) { float r; asm("ex2.approx.ftz.f32 %0, %1;" : "=f"(r) : "f"(x)); return r; }
__device__ __forceinline__ void stmatrix4(uint32_t addr, uint32_t a, uint32_t b, uint32_t c, uint32_t d) {
  asm volatile("stmatrix.sync.aligned.m8n8.x4.shared.b16 [%0], {%1,%2,%3,%4};" ::"r"(addr), "r"(a), "r"(b), "r"(c), "r"(d) : "memory");
}
__device__ __forceinline__ void ldmatrix4(uint32_t addr, uint32_t& a, uint32_t& b, uint32_t& c, uint32_t& d) {
  asm volatile("ldmatrix.sync.aligned.m8n8.x4.shared.b16 {%0,%1,%2,%3}, [%4];" : "=r"(a), "=r"(b), "=r"(c), "=r"(d) : "r"(addr) : "memory");
}
__device__ __forceinline__ void ldmatrix4t(uint32_t addr, uint32_t& a, uint32_t& b, uint32_t& c, uint32_t& d) {
  asm volatile("ldmatrix.sync.aligned.m8n8.x4.trans.shared.b16 {%0,%1,%2,%3}, [%4];" : "=r"(a), "=r"(b), "=r"(c), "=r"(d) : "r"(addr) : "memory");
}
__device__ __forceinline__ void mma16816(float (&d)[4], uint32_t a0, uint32_t a1, uint32_t a2, uint32_t a3, uint32_t b0, uint32_t b1) {
  asm volatile("mma.sync.aligned.m16n8k16.row.col.f32.bf16.bf16.f32 {%0,%1,%2,%3}, {%4,%5,%6,%7}, {%8,%9}, {%0,%1,%2,%3};"
               : "+f"(d[0]), "+f"(d[1]), "+f"(d[2]), "+f"(d[3]) : "r"(a0), "r"(a1), "r"(a2), "r"(a3), "r"(b0), "r"(b1));
}
__device__ __forceinline__ void sts1(uint32_t a, uint32_t v) { asm volatile("st.shared.u32 [%0], %1;" ::"r"(a), "r"(v) : "memory"); }
__device__ __forceinline__ uint4 lds4(uint32_t a) {
  uint4 v; asm volatile("ld.shared.v4.u32 {%0,%1,%2,%3}, [%4];" : "=r"(v.x), "=r"(v.y), "=r"(v.z), "=r"(v.w) : "r"(a) : "memory"); return v;
}
__device__ __forceinline__ uint2 lds2(uint32_t a) {
  uint2 v; asm volatile("ld.shared.v2.u32 {%0,%1}, [%2];" : "=r"(v.x), "=r"(v.y) : "r"(a) : "memory"); return v;
}
__device__ __forceinline__ uint32_t lds1(uint32_t a) {
  uint32_t v; asm volatile("ld.shared.u32 %0, [%1];" : "=r"(v) : "r"(a) : "memory"); return v;
}
__device__ __forceinline__ void sts2(uint32_t a, uint32_t x, uint32_t y) { asm volatile("st.shared.v2.u32 [%0], {%1,%2};" ::"r"(a), "r"(x), "r"(y) : "memory"); }
__device__ __forceinline__ void sts4(uint32_t a, uint4 v) {
  asm volatile("st.shared.v4.u32 [%0], {%1,%2,%3,%4};" ::"r"(a), "r"(v.x), "r"(v.y), "r"(v.z), "r"(v.w) : "memory");
}
__device__ __forceinline__ float silu_f(float v) { return v * rcp(1.f + ex2(v * -1.4426950408889634f)); }
__device__ __forceinline__ uint32_t hfma2(uint32_t a, uint32_t b, uint32_t c) {
  uint32_t r; asm("fma.rn.bf16x2 %0, %1, %2, %3;" : "=r"(r) : "r"(a), "r"(b), "r"(c)); return r;
}
__device__ __forceinline__ void split_inv(float sd, uint32_t& ih, uint32_t& il) {
  const float inv = rcp(sd);
  ih = pack_bf(inv, inv);
  const float lo = inv - bf_lo(ih);
  il = pack_bf(lo, lo);
}
__device__ __forceinline__ uint32_t ln_norm(uint32_t x, uint32_t mean2, uint32_t ih, uint32_t il) {
  const uint32_t d = hsub2(x, mean2);
  return hfma2(d, ih, hmul2(d, il));
}
__device__ __forceinline__ uint32_t ln_mod(uint32_t x, uint32_t mean2, uint32_t ih, uint32_t il, uint32_t c1, uint32_t sh) {
  return hadd2(hmul2(ln_norm(x, mean2, ih, il), c1), sh);
}

#define R8(a, i) "+f"(a[i]), "+f"(a[i + 1]), "+f"(a[i + 2]), "+f"(a[i + 3]), "+f"(a[i + 4]), "+f"(a[i + 5]), "+f"(a[i + 6]), "+f"(a[i + 7])
#define D64 "{%0,%1,%2,%3,%4,%5,%6,%7,%8,%9,%10,%11,%12,%13,%14,%15,%16,%17,%18,%19,%20,%21,%22,%23,%24,%25,%26,%27,%28,%29,%30,%31," \
            "%32,%33,%34,%35,%36,%37,%38,%39,%40,%41,%42,%43,%44,%45,%46,%47,%48,%49,%50,%51,%52,%53,%54,%55,%56,%57,%58,%59,%60,%61,%62,%63}"
template <int TB>
__device__ __forceinline__ void mma_ss(float (&d)[64], uint64_t da, uint64_t db, int sc) {
  asm volatile("{\n.reg .pred p;\nsetp.ne.b32 p, %66, 0;\n"
               "wgmma.mma_async.sync.aligned.m64n128k16.f32.bf16.bf16 " D64 ", %64, %65, p, 1, 1, 0, %67;\n}"
               : R8(d, 0), R8(d, 8), R8(d, 16), R8(d, 24), R8(d, 32), R8(d, 40), R8(d, 48), R8(d, 56)
               : "l"(da), "l"(db), "r"(sc), "n"(TB));
}
template <int TB>
__device__ __forceinline__ void mma_rs(float (&d)[64], uint32_t a0, uint32_t a1, uint32_t a2, uint32_t a3, uint64_t db, int sc) {
  asm volatile("{\n.reg .pred p;\nsetp.ne.b32 p, %69, 0;\n"
               "wgmma.mma_async.sync.aligned.m64n128k16.f32.bf16.bf16 " D64 ", {%64,%65,%66,%67}, %68, p, 1, 1, %70;\n}"
               : R8(d, 0), R8(d, 8), R8(d, 16), R8(d, 24), R8(d, 32), R8(d, 40), R8(d, 48), R8(d, 56)
               : "r"(a0), "r"(a1), "r"(a2), "r"(a3), "l"(db), "r"(sc), "n"(TB));
}
#define D128 "{%0,%1,%2,%3,%4,%5,%6,%7,%8,%9,%10,%11,%12,%13,%14,%15,%16,%17,%18,%19,%20,%21,%22,%23,%24,%25,%26,%27,%28,%29,%30,%31," \
             "%32,%33,%34,%35,%36,%37,%38,%39,%40,%41,%42,%43,%44,%45,%46,%47,%48,%49,%50,%51,%52,%53,%54,%55,%56,%57,%58,%59,%60,%61,%62,%63," \
             "%64,%65,%66,%67,%68,%69,%70,%71,%72,%73,%74,%75,%76,%77,%78,%79,%80,%81,%82,%83,%84,%85,%86,%87,%88,%89,%90,%91,%92,%93,%94,%95," \
             "%96,%97,%98,%99,%100,%101,%102,%103,%104,%105,%106,%107,%108,%109,%110,%111,%112,%113,%114,%115,%116,%117,%118,%119,%120,%121,%122,%123,%124,%125,%126,%127}"
#define R128(d, e) R8(d, 0), R8(d, 8), R8(d, 16), R8(d, 24), R8(d, 32), R8(d, 40), R8(d, 48), R8(d, 56), \
                   R8(e, 0), R8(e, 8), R8(e, 16), R8(e, 24), R8(e, 32), R8(e, 40), R8(e, 48), R8(e, 56)
__device__ __forceinline__ void mma256_ss(float (&d)[64], float (&e)[64], uint64_t da, uint64_t db, int sc) {
  asm volatile("{\n.reg .pred p;\nsetp.ne.b32 p, %130, 0;\n"
               "wgmma.mma_async.sync.aligned.m64n256k16.f32.bf16.bf16 " D128 ", %128, %129, p, 1, 1, 0, 1;\n}"
               : R128(d, e) : "l"(da), "l"(db), "r"(sc));
}
__device__ __forceinline__ void mma256_rs(float (&d)[64], float (&e)[64], uint32_t a0, uint32_t a1, uint32_t a2, uint32_t a3, uint64_t db) {
  asm volatile("{\n.reg .pred p;\nsetp.ne.b32 p, 1, 0;\n"
               "wgmma.mma_async.sync.aligned.m64n256k16.f32.bf16.bf16 " D128 ", {%128,%129,%130,%131}, %132, p, 1, 1, 1;\n}"
               : R128(d, e) : "r"(a0), "r"(a1), "r"(a2), "r"(a3), "l"(db));
}
template <int N> __device__ __forceinline__ void keep(float (&a)[N]) {
#pragma unroll
  for (int i = 0; i < N; i++) asm volatile("" : "+f"(a[i])::"memory");
}
template <int N> __device__ __forceinline__ void keep(uint32_t (&a)[N]) {
#pragma unroll
  for (int i = 0; i < N; i++) asm volatile("" : "+r"(a[i])::"memory");
}

#define STAMP(idx) do {} while (0)
#define PROF(grp, cond, idx) do {} while (0)

constexpr float SCL2 = 1.4426950408889634f * 0.08838834764831845f;

__device__ __forceinline__ void pack_p(const float (&s)[64], uint32_t (&p)[32]) {
#pragma unroll
  for (int i = 0; i < 32; i++) p[i] = pack_bf(s[2 * i], s[2 * i + 1]);
}

__device__ __forceinline__ void issue_qk(float (&s)[64], uint32_t q0, uint32_t q1, uint32_t kslot) {
  const uint64_t db = make_desc(kslot, 16, 1024), da0 = make_desc(q0, 16, 1024), da1 = make_desc(q1, 16, 1024);
#pragma unroll
  for (int kk = 0; kk < 8; kk++) mma_ss<0>(s, (kk < 4 ? da0 : da1) + (kk & 3) * 2, db + (kk >> 2) * 1024 + (kk & 3) * 2, kk != 0);
}
__device__ __forceinline__ void issue_pv(float (&o)[64], uint32_t (&p)[32], uint32_t vslot, int acc) {
  uint64_t db = make_desc(vslot, 16384, 1024);
#pragma unroll
  for (int kk = 0; kk < 8; kk++)
    mma_rs<1>(o, p[4 * kk], p[4 * kk + 1], p[4 * kk + 2], p[4 * kk + 3], db + kk * 128, kk == 0 ? acc : 1);
}

template <int H>
__device__ __forceinline__ void store_chunk(const float (&a)[64], uint32_t addr) {
#pragma unroll
  for (int i = 8 * H; i < 8 * H + 8; i += 2)
    stmatrix4(addr ^ ((i & 7) << 4), pack_bf(a[4 * i], a[4 * i + 1]), pack_bf(a[4 * i + 2], a[4 * i + 3]),
              pack_bf(a[4 * i + 4], a[4 * i + 5]), pack_bf(a[4 * i + 6], a[4 * i + 7]));
}
template <int H>
__device__ __forceinline__ void store_chunk(const float (&a)[64], float i0, float i1, uint32_t addr) {
#pragma unroll
  for (int i = 8 * H; i < 8 * H + 8; i += 2)
    stmatrix4(addr ^ ((i & 7) << 4), pack_bf(a[4 * i] * i0, a[4 * i + 1] * i0), pack_bf(a[4 * i + 2] * i1, a[4 * i + 3] * i1),
              pack_bf(a[4 * i + 4] * i0, a[4 * i + 5] * i0), pack_bf(a[4 * i + 6] * i1, a[4 * i + 7] * i1));
}
__device__ __forceinline__ float inv_quad_sum(float l) {
  l += __shfl_xor_sync(0xffffffffu, l, 1);
  l += __shfl_xor_sync(0xffffffffu, l, 2);
  return rcp(l);
}

__device__ __forceinline__ void write_table(uint32_t table, bool ca, uint32_t t, const uint4& m0, const uint4& m1) {
  float c0 = untag_sum(m0.x, m1.x), c1 = untag_sum(m0.y, m1.y), c2 = untag_sum(m0.z, m1.z), c3 = untag_sum(m0.w, m1.w);
  if (ca) { c0 = 1.f + rbf(c0); c1 = 1.f + rbf(c1); c2 = 1.f + rbf(c2); c3 = 1.f + rbf(c3); }
  const uint32_t d = table + (t >> 2) * 64 + (t & 1) * 32 + (t & 2) * 2 + (ca ? 0 : 8);
  sts1(d, pack_bf(c0, c1));
  sts1(d + 16, pack_bf(c2, c3));
}

__device__ __forceinline__ void ln_scalars(float mean, float var, float& mb, float& sd) {
  mb = rbf(mean);
  float r; asm("sqrt.approx.ftz.f32 %0, %1;" : "=f"(r) : "f"(rbf(rbf(var) + 1e-5f)));
  sd = rbf(r);
}

__global__ void __cluster_dims__(2, 1, 1) __launch_bounds__(384, 1) fused_kernel(const Ptrs P, const __grid_constant__ Maps maps) {
  extern __shared__ __align__(1024) uint8_t smem_raw[];
  const uint32_t base = smem_u32(smem_raw);
  const int tid = threadIdx.x, lane = tid & 31;
  const int warp = __shfl_sync(0xffffffffu, tid >> 5, 0);
  int b = blockIdx.x;
  {
    const uint32_t p = b >> 1, q = (p - 36) * 37 >> 8, r = p - 36 - 7 * q;
    const uint32_t w = p < 4 ? 60 + p : (p < 36 ? ((p + 2) & 7) * 8 + ((p - 4) >> 3) : (r ? r - 1 : 6) * 8 + 4 + q);
    b = p < 64 ? w * 2 + (b & 1) : b;
  }
  PROF(31, tid == 0, 0);

  if (b >= NMAIN) {
    float* sc = reinterpret_cast<float*>(smem_raw);
    float* red = sc + DM;
    for (int k = tid; k < DM; k += 384) sc[k] = rbf(silu_f(__bfloat162float(P.c[k])));
    __syncthreads();
    if (tid < 256) {
      const int col = 2048 + (b - NMAIN) * 1024 + (tid & 127) * 8, r0 = (tid >> 7) * 512;
      float acc[8];
#pragma unroll
      for (int e = 0; e < 8; e++) acc[e] = 0.f;
#pragma unroll 1
      for (int r = r0; r < r0 + 512; r += HU) {
        uint4 w[HU];
#pragma unroll
        for (int u = 0; u < HU; u++) w[u] = ldg_stream4(P.w_mod + (size_t)(r + u) * NMOD + col);
#pragma unroll
        for (int u = 0; u < HU; u++) {
          float s = sc[r + u];
          acc[0] += s * bf_lo(w[u].x); acc[1] += s * bf_hi(w[u].x); acc[2] += s * bf_lo(w[u].y); acc[3] += s * bf_hi(w[u].y);
          acc[4] += s * bf_lo(w[u].z); acc[5] += s * bf_hi(w[u].z); acc[6] += s * bf_lo(w[u].w); acc[7] += s * bf_hi(w[u].w);
        }
      }
      if (tid >= 128) {
#pragma unroll
        for (int e = 0; e < 8; e++) red[(tid & 127) * 8 + e] = acc[e];
      }
      const uint32_t tag = ld_relaxed(&g_epoch) % 3 + 1;
      bar_sync(1, 256);
      if (tid < 128) {
        uint32_t o[8];
#pragma unroll
        for (int e = 0; e < 8; e++) o[e] = __float_as_uint(rbf(acc[e] + red[tid * 8 + e])) | tag;
        st_relaxed4(g_mod + col, o[0], o[1], o[2], o[3]);
        st_relaxed4(g_mod + col + 4, o[4], o[5], o[6], o[7]);
        const uint4 wr = ldg_nc4(P.w_r + tid * 8);
        const uint32_t wv[4] = {wr.x, wr.y, wr.z, wr.w};
        float dsum = 0.f;
#pragma unroll
        for (int e = 0; e < 8; e++) {
          const float m = bf_hi(o[e]);
          dsum += (b == NMAIN + 2 ? rbf(1.f + m) : m) * ((e & 1) ? bf_hi(wv[e >> 1]) : bf_lo(wv[e >> 1]));
        }
#pragma unroll
        for (int k = 16; k > 0; k >>= 1) dsum += __shfl_xor_sync(0xffffffffu, dsum, k);
        if (lane == 0) st_relaxed(g_mod + (b - NMAIN) * 4 + warp, tagf(dsum, tag));
      }
    }
    PROF(2, tid == 0, 1);
    return;
  }

  const int rank = b & 1;
  const int rb = ((b >> 4) << 1) | rank, cj = (b >> 1) & 7;
  const bool late = b & 4;
  const uint32_t bfull = base + OFF_BAR, bempty = bfull + NSLOT * 8;
  const uint32_t gfull = bempty + NSLOT * 8, gempty = gfull + 32;
  const uint32_t bar_ofull = gempty + 32;
  const uint32_t bar_ofree = bar_ofull + 32;
  const uint32_t bar_par = bar_ofree + 32;
  const uint32_t bar_mod = bar_par + 8;
  const uint32_t bar_pread = bar_mod + 8;
  const uint32_t bar_xres = bar_pread + 8;
  const uint32_t bar_ring = bar_xres + 8;
  const uint32_t bar_box = bar_ring + 24;
  const uint32_t bar_go = bar_box + 96;
  const uint32_t bar_go2 = bar_go + 16;
  const uint32_t bar_cnt = bar_go + 24;
  const uint32_t xfull = bar_go + 40, xempty = xfull + 32;
  const uint32_t bar_hw = xempty + 32, bar_hx = bar_hw + 8;
  const uint32_t bar_hpub = bar_hx + 16;
  const uint32_t bar_win = bar_hpub + 16;
  const uint32_t bar_rx = bar_win + 8;
  const uint32_t bar_sel = bar_rx + 8;
  const uint32_t bar_gate = bar_sel + 8;
  const uint32_t bar_rel = bar_gate + 8;
  const uint32_t bar_od = bar_rel + 8;
  const uint32_t bar_mod2 = bar_od + 8;
  const uint32_t bar_res = bar_go + 8;
  const uint32_t stage = base + OFF_STAGE, par = base + OFF_PAR;

  if (warp == 9 && elect_one()) {
    mbar_init(bar_hw, 1); mbar_init(bar_hx, 1); mbar_init(bar_hx + 8, 1);
    asm volatile("fence.mbarrier_init.release.cluster;" ::: "memory");
    mbar_expect_tx(bar_hw, 32768);
    mbar_expect_tx(bar_hx, 16384);
    mbar_expect_tx(bar_hx + 8, 16384);
    const __nv_bfloat16* xs = P.x + (size_t)(rb * 128 + cj * 16) * DM;
    bulk_load(base + 2 * GST_BYTES, xs, 16384, bar_hx);
    if (!late) {
      tma2d(stage, &maps.wm, (b >> 1) * 32, rank * 512, bar_hw);
      tma2d(stage + 16384, &maps.wm, (b >> 1) * 32, rank * 512 + 256, bar_hw);
    }
    bulk_load(base + 3 * GST_BYTES, xs + 8 * DM, 16384, bar_hx + 8);
  }
  if (warp == 10 && elect_one()) prefetch_map(&maps.wm);
  if (warp == 8 && elect_one()) {
    for (int s = 0; s < NSLOT; s++) { mbar_init(bfull + s * 8, 1); mbar_init(bempty + s * 8, 16); }
    for (int s = 0; s < 4; s++) { mbar_init(gfull + s * 8, 1); mbar_init(gempty + s * 8, 16); mbar_init(xfull + s * 8, 1); mbar_init(xempty + s * 8, 8); mbar_init(bar_ofree + s * 8, 1); mbar_init(bar_ofull + s * 8, 128); }
    mbar_init(bar_par, 64); mbar_init(bar_mod, 256); mbar_init(bar_pread, 2); mbar_init(bar_xres, 1);
    mbar_init(bar_ring, 8); mbar_init(bar_ring + 8, 8); mbar_init(bar_ring + 16, 8);
    mbar_init(bar_go, 1); mbar_init(bar_go2, 1); mbar_init(bar_cnt, 1); mbar_init(bar_cnt + 8, 1); mbar_init(bar_hpub, 8); mbar_init(bar_hpub + 8, 8); mbar_init(bar_res, 1); mbar_init(bar_win, 1); mbar_init(bar_rx, 1); mbar_init(bar_sel, 64); mbar_init(bar_gate, 8); mbar_init(bar_rel, 8); mbar_init(bar_od, 1); mbar_init(bar_mod2, 64);
    for (int s = 0; s < 12; s++) mbar_init(bar_box + s * 8, 1);
    asm volatile("fence.mbarrier_init.release.cluster;" ::: "memory");
    prefetch_map(&maps.x); prefetch_map(&maps.wq); prefetch_map(&maps.k); prefetch_map(&maps.v);
  }
  cluster_arrive();

  if (warp >= 8) {
    asm volatile("setmaxnreg.dec.sync.aligned.u32 40;");
    if (warp < 10) bar_arrive(1, 320);
    const uint32_t epoch = ld_relaxed(&g_epoch);
    cluster_wait();
    if (warp == 8) {
      const int kvrow = (cj >> 1) * SK + (SK - WIN);
      int wch = cj * 8 + rank * 2;
#pragma unroll 1
      for (int ps = 0; ps < 3; ps++) {
        const CUtensorMap* mw = ps == 2 ? &maps.wo : &maps.wq;
        const uint32_t xt = ps == 1 ? XT1 : XT2, wt = ps == 0 ? WT0 : (ps == 1 ? WT1 : WT2);
        const int nst = ps == 2 ? 32 : 16;
#pragma unroll 1
        for (int i = 0; i < nst; i++) {
          const uint32_t bf = gfull + (i & 3) * 8;
          const int kt = ps == 2 ? (((cj & 1) * 4 + ((i >> 1) & 3)) * 4 + (i >> 3)) * 2 + (i & 1) : (ps ? i : slice_of(i) + (b & 14)) & 15;
          const uint32_t wd = base + unit_of(wt, i & 3) + rank * UNIT, xd = base + unit_of(xt, i & 3);
          const uint8_t* xs = g_act + (uint32_t)(rb * 80 + (ps - 1) * 16 + kt) * UNIT;
          if (ps == 0 && i == HD) mbar_wait(bar_mod, 0);
          if (ps == 2 && (i & 7) == 0 && i != 8) mbar_wait(i ? bar_cnt + i - 16 : bar_ofree + 24, 0);
          if ((i & 7) == 0) fence_async();
          if (i == RES0) mbar_wait(bar_res, 0);
          mbar_wait(bf, ((i >> 2) & 1) ^ 1);
          if (elect_one()) {
            mbar_expect_tx(bf, ps ? GST_BYTES : 2 * UNIT);
            if (ps && i < 2) bulk_load_stream(xd, xs, UNIT, bf);
            mbar_arrive_pred(bar_go, i == GOST);
            mbar_arrive_pred(bar_go2, ps == 1 && i == PG0);
            mbar_arrive_pred(bar_od, ps && i == (ps == 1 ? ODS1 : ODS) + 1);
            if (i == RES0) mbar_expect_tx(bar_xres, 32768);
          }
          const int wk = (i == 31 ? kt ^ (rank * 32) : kt) * 64, wc = i == 31 ? cj * 2 : wch;
          const uint64_t xp = i == 31 ? l2_normal() : l2_stream();
          mbar_wait(ps && i < 4 ? bempty + i * 8 : gempty + (i & 3) * 8, ((i >> 2) & 1) ^ 1);
          if (elect_one()) {
            tma3d_mc<true>(wd, mw, 0, wk, wc, bf);
            if (ps && i > 2) bulk_load_stream(xd, xs, UNIT, bf, xp);
            if (i == RES0 || i == RES1) tma2d(base + OFF_RES + (i == RES1) * UNIT, &maps.x, cj * 128 + (i == RES1) * 64, rb * 128, bar_xres);
          }
          if (ps && i == 2) {
            mbar_wait(bar_ofree + (ps - 1) * 16, 0);
            if (elect_one()) bulk_load_stream(xd, xs, UNIT, bf);
          }
        }
        if (ps == 2) break;
        wch = ps ? ((wch >> 3) ^ rank) * 2 : wch + 4;
#pragma unroll 1
        for (int u = 0; u < 16; u++) {
          const bool isk = (u == 0) || ((u & 1) && u < 15), kept = (0x1680 >> u) & 1;
          const int blk = (0x472FAD84u >> (u * 2)) & 3;
          const uint32_t sl = base + unit_of(ps ? AT1 : AT0, u & 3) + rank * UNIT, bf = bfull + (u & 3) * 8;
          mbar_wait(bf, ((u >> 2) & 1) ^ 1);
          if (!kept && elect_one()) mbar_expect_tx(bf, SLOT_BYTES);
          mbar_wait(u < 4 ? gempty + ((u + 1) >> 1) * 8 : bempty + (u & 3) * 8, ((u >> 2) & 1) ^ 1);
          if (elect_one()) {
            if (kept) mbar_arrive(bf);
            else if (ps && (blk >= 2 || u > 8)) tma3d_mc<true>(sl, isk ? &maps.k : &maps.v, 0, kvrow + blk * 128, rank, bf);
            else tma3d_mc<false>(sl, isk ? &maps.k : &maps.v, 0, kvrow + blk * 128, rank, bf);
          }
        }
      }
      if (elect_one()) mbar_expect_tx(bar_rx, UNIT);
      mbar_wait(bar_rel, 0);
      if (elect_one()) {
        bulk_load_stream(base + UNIT, g_act + (uint32_t)(rb * 80 + 16 + 63 - (cj & 1) * 32) * UNIT, UNIT, bar_rx);
      }
      if (b < NFFN) {
#pragma unroll 1
        for (int u = 0; u < 12; u++) {
          const uint32_t dst = base + unit_of(u < 4 ? FT_G : (u < 8 ? FT_U : FT_D), u & 3);
          if (elect_one()) mbar_expect_tx(bar_box + u * 8, UNIT);
          if (u == 0 || u == 2 || u == 8) mbar_wait(bar_ring + (u == 8 ? 16 : u * 4), 0);
          const int fp = u < 8 ? FPACE0 : FPACE;
          if (u >= fp) mbar_wait(bar_box + (u - fp) * 8, 0);
          if (elect_one()) {
            if (u < 8) tma2d(dst, u < 4 ? &maps.wg : &maps.wu, b * 32, (u & 3) * 256, bar_box + u * 8);
            else tma3d(dst, &maps.wd, 0, b * 32, (u - 8) * 4, bar_box + u * 8);
          }
        }
      }
    } else if (warp == 9) {
      const uint32_t target = 8 * (epoch + 1);
      uint32_t hmask = 0;
#pragma unroll 1
      for (int i = 0; i < 16; i++) {
        if (i == HDX) mbar_wait(bar_mod, 0);
        const int kt = (2 * cj + slice_of(i)) & 15;
        const uint32_t need = i == 15 ? 0xffffu : 1u << kt;
        if (i >= NRS && (hmask & need) != need) {
          uint32_t n = 0;
          do { hmask = __ballot_sync(0xffffffffu, ld_acquire(&g_cnt_h[rb * 32 + (lane & 15)]) == epoch + 1); watchdog(n); } while ((hmask & need) != need);
          PROF(1, lane == 0 && i == NRS, 26);
          fence_async();
        }
        mbar_wait(xempty + (i & 3) * 8, ((i >> 2) & 1) ^ 1);
        if (elect_one()) {
          mbar_expect_tx(xfull + (i & 3) * 8, UNIT);
          if (i < NRS) tma2d(base + (i & 3) * GST_BYTES, &maps.x, kt * 64, rb * 128, xfull + (i & 3) * 8);
          else bulk_load_stream(base + (i & 3) * GST_BYTES, g_act + (uint32_t)(rb * 80 + kt) * UNIT, UNIT, xfull + (i & 3) * 8);
        }
      }
      prefetch_map(&maps.wo);
#pragma unroll 1
      for (int t = 0; t < 4; t++) {
        if (t & 1) mbar_wait(bar_od, t >> 1);
        const int ops = OPS >> (t & 1);
#pragma unroll 1
        for (int p = 0; p < 32768; p += ops) {
          const uint32_t w = p >> 14, c = (p >> 13) & 1, off = w * 8192 + (p & 8191);
          mbar_wait(bar_ofull + (t & 1) * 16 + w * 8, t >> 1);
          if (elect_one()) {
            bulk_store(g_act + (uint32_t)(rb * 80 + 16 + (cj * 4 + t) * 2 + c) * UNIT + off, base + unit_of(QT, 2 * t + c) + off, ops);
            asm volatile("cp.async.bulk.commit_group;" ::: "memory");
            asm volatile("cp.async.bulk.wait_group.read 0;" ::: "memory");
          }
        }
        if (elect_one()) {
          mbar_arrive(t < 3 ? bar_ofree + t * 8 : bar_res);
          asm volatile("cp.async.bulk.wait_group 0;" ::: "memory");
          fence_async();
          red_release(&g_cnt_o[((rb * 4 + t) * 2 + (cj >> 2)) * 32], 2);
        }
        if (t) {
          wait_counter(&g_cnt_o[(rb * 8 + 2 * t + (cj & 1)) * 32], target);
          if (t & 1) wait_counter(&g_cnt_o[(rb * 8 + (t == 1 ? cj & 1 : 7 - (cj & 1))) * 32], target);
          if (elect_one()) mbar_arrive(t == 1 ? bar_ofree + 24 : bar_cnt + t * 8 - 16);
        }
      }
      PROF(2, lane == 0, 27);
      const uint32_t tag = epoch % 3 + 1;
      const uint32_t* inbox = g_cand + (b >> 4) % CR * 512 + (lane & 15) * CS;
      mbar_wait(bar_ring + 16, 0);
      uint32_t c0 = ld_relaxed(inbox), n = 0;
#define CAND_STEP(cv)                                                                                        \
      {                                                                                                      \
        const bool valid = (cv & 3u) == tag, all = __all_sync(0xffffffffu, valid);                           \
        const uint32_t best = __reduce_max_sync(0xffffffffu, valid ? cv : 0u);                               \
        const uint32_t blk = __ffs(__ballot_sync(0xffffffffu, cv == best)) - 1;                              \
        const uint32_t st = (blk << 7 | (~best >> 2 & 127)) | (all ? 0x1800 : 0x800);                        \
        if (best) asm volatile("st.volatile.shared.v2.u32 [%0], {%1, %2};" ::"r"(par + PAR_CONST + 56), "r"(best), "r"(st) : "memory"); \
        if (all) break;                                                                                      \
        cv = ld_relaxed(inbox);                                                                              \
      }
      while (true) { CAND_STEP(c0) watchdog(n); }
    } else {
      const int t2 = tid - 320;
      if (late && warp == 10) {
        mbar_wait(bar_hx, 0);
        if (elect_one()) {
          tma2d(stage, &maps.wm, (b >> 1) * 32, rank * 512, bar_hw);
          tma2d(stage + 16384, &maps.wm, (b >> 1) * 32, rank * 512 + 256, bar_hw);
        }
      }
      {
        const uint32_t tag = epoch % 3 + 1;
        mbar_wait(bar_hx + 8, 0);
        mbar_wait(bar_hw, 0);
        __nanosleep(late ? OSL2 : OSL);
        {
          const uint32_t t7 = (warp & 1) * 64 + (lane >> 4) * 32 + 16 + (lane & 15);
          const uint32_t* pm = g_modp + ((cj * 128 + t7 * 4) & (DM - 1));
          uint4 m0, m1, m2, m3;
          uint32_t n = 0;
          do {
            m0 = ld_relaxed4(pm); m1 = ld_relaxed4(pm + 2 * DM); m2 = ld_relaxed4(pm + DM); m3 = ld_relaxed4(pm + 3 * DM);
            watchdog(n);
          } while (!__all_sync(0xffffffffu, tag_ok(m0, tag) && tag_ok(m1, tag) && tag_ok(m2, tag) && tag_ok(m3, tag)));
          write_table(par, false, t7, m0, m1);
          write_table(par, true, t7, m2, m3);
          mbar_arrive(bar_mod2);
        }
      }
      mbar_wait(bar_hpub + (warp & 1) * 8, 0);
      PROF(1, t2 == 0, 24);
#pragma unroll 1
      for (int c = 0; c < 8; c++) {
        const uint32_t off = (warp & 1) * UNIT + c * 2048 + lane * 16;
        uint8_t* dst = g_act + (uint32_t)(rb * 80 + cj * 2) * UNIT + off;
        const uint4 v0 = lds4(stage + off), v1 = lds4(stage + off + 512), v2 = lds4(stage + off + 1024), v3 = lds4(stage + off + 1536);
        stg4(dst, v0); stg4(dst + 512, v1); stg4(dst + 1024, v2); stg4(dst + 1536, v3);
      }
      __syncwarp();
      PROF(1, t2 == 0, 15);
      if (lane == 0) {
        mbar_arrive(bar_pread);
        red_release(&g_cnt_h[rb * 32 + cj * 2 + (warp & 1)], 1);
        PROF(1, t2 == 0, 25);
        prefetch_map(&maps.wg); prefetch_map(&maps.wu); prefetch_map(&maps.wd); prefetch_map(&maps.out);
      }
      __syncwarp();
      if (b < NFFN) {
        mbar_wait(bar_go2, 0);
        const __nv_bfloat16* pg = ((b & 1) ? P.w_up : P.w_gate) + (b >> 1) * 64 + (size_t)t2 * FF;
        const __nv_bfloat16* pd = P.w_down + (size_t)b * 32768 + t2 * 64;
        PROF(2, t2 == 0, 13);
#pragma unroll 1
        for (int i = 0; i < WN; i += WB) {
          uint32_t v[WB];
#pragma unroll
          for (int u = 0; u < WB; u++) {
            const int k = i + u;
            asm volatile("ld.global.cg.L2::128B.u32 %0, [%1];" : "=r"(v[u]) : "l"(k < 16 ? pg + (size_t)k * 64 * FF : pd + (k - 16) * 4096));
          }
#pragma unroll
          for (int u = 1; u < WB; u++) v[0] ^= v[u];
          sts1(par + PAR_SINK + t2 * 4, v[0]);
        }
        PROF(2, t2 == 0, 14);
      }
      const uint32_t tag = epoch % 3 + 1;
      mbar_wait(bar_go, 0);
      bar_sync(4, 64);
      if (warp == 10) {
        const uint32_t* src = g_mod + 2 * DM + cj * 128 + lane * 4;
        const uint2 wr = *reinterpret_cast<const uint2*>(P.w_r + cj * 128 + lane * 4);
        uint4 vga, vsb, vcb, vgb;
        uint32_t n = 0;
        do {
          vga = ld_relaxed4(src); vsb = ld_relaxed4(src + DM); vcb = ld_relaxed4(src + 2 * DM); vgb = ld_relaxed4(src + 3 * DM);
          watchdog(n);
        } while (!__all_sync(0xffffffffu, tag_ok(vga, tag) && tag_ok(vsb, tag) && tag_ok(vcb, tag) && tag_ok(vgb, tag)));
        const float c0 = rbf(1.f + bf_hi(vcb.x)), c1 = rbf(1.f + bf_hi(vcb.y)), c2 = rbf(1.f + bf_hi(vcb.z)), c3 = rbf(1.f + bf_hi(vcb.w));
        const float a0 = c0 * bf_lo(wr.x), a1 = c1 * bf_hi(wr.x), a2 = c2 * bf_lo(wr.y), a3 = c3 * bf_hi(wr.y);
        const uint32_t h0 = pack_bf(a0, a1), h1 = pack_bf(a2, a3);
        const uint32_t t1 = par + PAR_T1 + (lane >> 2) * 64 + (lane & 1) * 32 + (lane & 2) * 2;
        sts1(t1, h0); sts1(t1 + 8, pack_bf(a0 - bf_lo(h0), a1 - bf_hi(h0)));
        sts1(t1 + 16, h1); sts1(t1 + 24, pack_bf(a2 - bf_lo(h1), a3 - bf_hi(h1)));
        const uint32_t tg = par + PAR_SINK + (lane >> 3) * 64 + (lane & 1) * 32 + (lane & 6) * 2;
        sts1(tg, __byte_perm(vga.x, vga.y, 0x7632)); sts1(tg + 16, __byte_perm(vga.z, vga.w, 0x7632));
        sts4(par + PAR_T2 + lane * 32, make_uint4(pack_bf(c0, c1), __byte_perm(vsb.x, vsb.y, 0x7632), __byte_perm(vgb.x, vgb.y, 0x7632), __byte_perm(vga.x, vga.y, 0x7632)));
        sts4(par + PAR_T2 + lane * 32 + 16, make_uint4(pack_bf(c2, c3), __byte_perm(vsb.z, vsb.w, 0x7632), __byte_perm(vgb.z, vgb.w, 0x7632), __byte_perm(vga.z, vga.w, 0x7632)));
      } else {
        const uint4 g = poll4((lane & 8) ? g_mod + 8 - (lane & 1) * 4 : g_mod + 5 * DM + (b >> 4) * 128 + (lane & 7) * 16 + (b & 12), tag);
        sts1(par + PAR_CONST + 60, 0);
        if (lane < 8) sts1(par + PAR_CONST + 16 + lane * 4, (b & 2) ? ((b & 1) ? g.w : g.z) : ((b & 1) ? g.y : g.x));
        else if (lane < 10) sts2(par + PAR_CONST + (lane - 8) * 8, __float_as_uint(untag_sum(g.x, g.y) + untag_sum(g.z, g.w)), epoch);
      }
      __syncwarp();
#pragma unroll 1
      for (int q = 0; q < 32; q++) {
        st_b128(g_xch + ((size_t)b * 8 * 256 + q * 64 + t2) * 4, (epoch & 1) << 16, 0, 0, 0);
        __nanosleep(RSL);
      }
      for (int q = 0; q < 2; q++) st_relaxed4(g_stats + (((rb * 8 + q * 4 + (t2 >> 4)) * 8 + cj) * 16 + (t2 & 15)) * 4, 0, 0, 0, 0);
      if (b < NFFN)
        for (int q = 0; q < 2; q++) st_relaxed4(ypart_slot(b, q * 64 + t2), 0, 0, 0, 0);
      st_relaxed4(g_row + rb * 2 * DM + (t2 >> 5) * DM + cj * 128 + (t2 & 31) * 4, 0, 0, 0, 0);
      __threadfence();
      mbar_arrive(bar_par);
      mbar_wait(bar_gate, 0);
      uint32_t have = 0, n = 0;
      while (true) {
        uint32_t st;
        asm volatile("ld.volatile.shared.u32 %0, [%1];" : "=r"(st) : "r"(par + PAR_CONST + 60) : "memory");
        st >>= 7;
        if ((st & 31) != have) {
          const uint32_t* hsrc = g_row + (st & 15) * 2 * DM + t2 * 4;
          uint4 hv[4];
          bool ok = true;
#pragma unroll
          for (int i = 0; i < 4; i++) hv[i] = ld_pairs(hsrc + i * 256);
#pragma unroll
          for (int i = 0; i < 4; i++) {
            sts2(base + ((FT_G >> i * 4) & 15) * UNIT + (warp & 1) * 8192 + 256 + lane * 8, hv[i].x, hv[i].z);
            ok = ok && hv[i].y == tag && hv[i].w == tag;
          }
          have = __all_sync(0xffffffffu, ok) ? st & 31 : 0;
        }
        if ((st ^ have) == 32) break;
        watchdog(n);
      }
      mbar_arrive(bar_sel);
    }
    __syncwarp();
    cluster_arrive();
    {
      const uint32_t tag = epoch % 3 + 1, t3 = tid - 256;
      mbar_wait(bar_win, 0);
      uint2 win = lds2(par + PAR_CONST + 56);
      win.y &= 0x7ff;
      const uint32_t* fsrc = g_row + (win.y >> 7) * 2 * DM + (b >> 4) * 128 + (t3 & 7) * 16 + (b & 6) * 2 + ((b >> 2) & 2);
      const uint32_t* ysrc = ypart_slot(min(t3, NFFN - 1), b);
      uint2 fh = ld_pair(fsrc), fx = ld_pair(fsrc + DM);
      uint4 ya = ld_b128(ysrc);
      const float rwin = __uint_as_float(((int)win.x < 0 ? win.x & 0x7fffffffu : ~win.x) & ~0x1ffu);
      const float rs = rbf(rcp(1.f + __expf(-rbf(rwin))));
      uint32_t n = 0;
      while (__any_sync(0xffffffffu, fh.y != tag || fx.y != tag)) { fh = ld_pair(fsrc); fx = ld_pair(fsrc + DM); watchdog(n); }
      while (true) {
        const bool miss = ((ya.x & 1) | (ya.y & 1) << 1) != tag;
        if (!__any_sync(0xffffffffu, miss)) break;
        if (miss) ya = ld_b128(ysrc);
        watchdog(n);
      }
      PROF(8, t3 == 0, 5);
      float y[8] = {bf_lo(ya.x & ~1u), bf_hi(ya.x), bf_lo(ya.y & ~1u), bf_hi(ya.y), bf_lo(ya.z), bf_hi(ya.z), bf_lo(ya.w), bf_hi(ya.w)};
#pragma unroll
      for (int h = 4; h > 0; h >>= 1) {
        const bool up = lane & (h * 2);
#pragma unroll
        for (int e = 0; e < h; e++) y[e] = (up ? y[e + h] : y[e]) + __shfl_xor_sync(0xffffffffu, up ? y[e] : y[e + h], h * 2);
      }
      y[0] += __shfl_xor_sync(0xffffffffu, y[0], 1);
      if (!(lane & 1)) sts1(par + PAR_RED + 64 + t3 * 2, __float_as_uint(y[0]));
      bar_sync(4, 128);
      if (t3 < 8) {
        float y0 = 0.f;
#pragma unroll
        for (int w7 = 0; w7 < 7; w7++) y0 += __uint_as_float(lds1(par + PAR_RED + 64 + w7 * 32 + t3 * 4));
        const uint32_t gv = lds1(par + PAR_CONST + 16 + t3 * 4);
        const uint32_t upd = hmul2(pack_bf(y0, y0), pack_bf(rs, rs));
        const uint32_t r = hadd2(fx.x, hmul2(__byte_perm(gv, gv, 0x3232), hadd2(fh.x, upd)));
        reinterpret_cast<uint16_t*>(P.out)[(size_t)win.y * DM + (b >> 4) * 128 + t3 * 16 + (b & 15)] = (b & 1) ? r >> 16 : r;
        if (b == 0 && t3 == 0) st_relaxed(&g_epoch, epoch + 1);
      }
      PROF(31, t3 == 0, 36);
    }
    cluster_wait();
  } else {
    const int wg = warp >> 2;

    uint32_t tag;
    auto gemv = [&]() {
      const uint32_t l = fresh_lane(), fr = (l & 7) + (l >> 4) * 8, tq = l & 3, row = base + 2 * GST_BYTES + warp * 2048;
      const uint32_t wa = stage + warp * 4096 + fr * 64 + ((((l >> 3) & 1) ^ ((fr >> 1) & 3)) << 4);
      uint32_t sc[8];
#pragma unroll
      for (int k = 0; k < 8; k++) sc[k] = lds1(row + 128 + k * 16 + tq * 4);
      float d0[4] = {0.f, 0.f, 0.f, 0.f}, d1[4] = {0.f, 0.f, 0.f, 0.f};
      mbar_wait(bar_hw, 0);
#pragma unroll
      for (int ks = 0; ks < 4; ks++) {
        uint32_t w[8];
        ldmatrix4t(wa + ks * 1024, w[0], w[1], w[2], w[3]);
        ldmatrix4t((wa ^ 32) + ks * 1024, w[4], w[5], w[6], w[7]);
        mma16816(d0, w[0], w[1], w[2], w[3], sc[2 * ks], sc[2 * ks + 1]);
        mma16816(d1, w[4], w[5], w[6], w[7], sc[2 * ks], sc[2 * ks + 1]);
      }
      sts1(row + (tq * 8 + (l >> 2)) * 4, __float_as_uint((tq & 2) ? ((tq & 1) ? d1[2] : d1[0]) : ((tq & 1) ? d0[2] : d0[0])));
      bar_sync(1, 256);
      if (warp == 0) {
        float s = 0.f;
#pragma unroll
        for (int w8 = 0; w8 < 8; w8++) s += __uint_as_float(lds1(row + w8 * 2048 + l * 4));
        st_relaxed(g_modp + rank * 2 * DM + (b >> 1) * 32 + l, (__float_as_uint(s) & ~3u) | tag);
      }
      PROF(1, tid == 0, 3);
    };
    {
      uint32_t* const pmod = g_modp + rank * 2 * DM + (b >> 1) * 32 + lane;
      uint32_t* const pln = g_ln1 + (rb * 128 + cj * 16 + warp) * 4;
      const uint32_t cv = ldg_nc1(P.c + rank * 512 + tid * 2);
      const uint32_t epoch = ld_relaxed(&g_epoch);
      if (warp == 0) st_relaxed(pmod, 0);
      if (lane == 0) { st_b128(pln, 0, 0, 0, 0); st_b128(pln + 32, 0, 0, 0, 0); }
      asm volatile("setmaxnreg.inc.sync.aligned.u32 232;");
      bar_sync(1, 320);
      tag = epoch % 3 + 1;
#pragma unroll
      for (int part = 0; part < 3; part++) {
        if (!(part & 1)) {
          const uint32_t xa = base + (2 + part / 2) * GST_BYTES + warp * 2048 + lane * 16;
          mbar_wait(bar_hx + part * 4, 0);
          float s0 = 0.f, s1 = 0.f, q0 = 0.f, q1 = 0.f;
#pragma unroll
          for (int q = 0; q < 4; q++) {
            const uint4 xv = lds4(xa + q * 512);
            const uint32_t u[4] = {xv.x, xv.y, xv.z, xv.w};
#pragma unroll
            for (int e = 0; e < 4; e++) { const float lo = bf_lo(u[e]), hi = bf_hi(u[e]); s0 += lo; s1 += hi; q0 += lo * lo; q1 += hi * hi; }
          }
          s0 += s1; q0 += q1;
#pragma unroll
          for (int o = 16; o > 0; o >>= 1) { s0 += __shfl_xor_sync(0xffffffffu, s0, o); q0 += __shfl_xor_sync(0xffffffffu, q0, o); }
          const float mean = s0 * (1.f / DM);
          float mb, sd;
          ln_scalars(mean, fmaxf(q0 * (1.f / DM) - mean * mean, 0.f), mb, sd);
          uint32_t ih, il;
          split_inv(sd, ih, il);
          if (lane == 0) st_b128(pln + part * 16, pack_bf(mb, mb), ih, il, tag);
          PROF(1, tid == 0 && part == 2, 4);
        } else {
          __syncwarp();
          sts1(base + 2 * GST_BYTES + warp * 2048 + 128 + lane * 4, pack_bf(silu_f(bf_lo(cv)), silu_f(bf_hi(cv))));
          __syncwarp();
          if (!late) gemv();
        }
      }
      cluster_wait();
      if (wg == 1) bar_arrive(2, 256);
    }

    const uint32_t rempty = lane < 2 ? mapa(bempty, lane & 1) : 0;
    constexpr uint32_t GE = NSLOT * 8 + 32;
    float o[64], s[64];
#pragma unroll 1
    for (int ps = 0; ps < 3; ps++) {
      {
        const uint32_t xt = ps == 1 ? XT1 : XT2, wt = ps == 1 ? WT1 : WT2;
        const int nst = ps == 2 ? 28 : 14;
        if (ps == 0) {
          float ga[64], gb[64];
#pragma unroll
          for (int i = 0; i < 64; i++) { ga[i] = 0.f; gb[i] = 0.f; }
          uint32_t a[2][16];
          const uint32_t l = fresh_lane();
          uint32_t fa[4];
#pragma unroll
          for (int kk = 0; kk < 4; kk++) fa[kk] = (base + wg * 8192 + frag_offset(warp)) ^ (kk * 32);
          const uint32_t mt = par + (l & 3) * 16;
          auto fetch = [&](int i, uint32_t (&f)[16], uint32_t z) {
            mbar_wait(xfull + (i & 3) * 8, i >> 2);
#pragma unroll
            for (int kk = 0; kk < 4; kk++) ldmatrix4(fa[kk] + (i & 3) * GST_BYTES + z, f[4 * kk], f[4 * kk + 1], f[4 * kk + 2], f[4 * kk + 3]);
          };
          const bool oddw = warp & 2;
          uint4 r0, r1;
          {
            const uint32_t t7 = (warp & 1) * 64 + (l >> 4) * 32 + (l & 15);
            const uint32_t* pm = g_modp + wg * DM + ((cj * 128 + t7 * 4) & (DM - 1));
            const uint32_t* pr = g_ln1 + (rb * 128 + warp * 16 + (l >> 2)) * 4;
            uint4 m0 = make_uint4(tag, tag, tag, tag), m1 = m0;
            if (late) gemv();
            if (!oddw) { m0 = ld_relaxed4(pm); m1 = ld_relaxed4(pm + 2 * DM); }
            r0 = ld_b128(pr); r1 = ld_b128(pr + 32);
            fetch(0, a[0], 0); fetch(1, a[1], 0);
            uint32_t n = 0;
            bool written = false;
#pragma unroll 1
            while (true) {
              uint32_t miss;
              asm volatile("{ .reg .pred p0, p1, p2, p3; .reg .b32 t, u;\n"
                           "lop3.b32 t, %1, %2, %19, 0x7e; lop3.b32 u, %3, %4, %19, 0x7e; or.b32 t, t, u; and.b32 t, t, 3; setp.ne.u32 p0, t, 0;\n"
                           "lop3.b32 t, %5, %6, %19, 0x7e; lop3.b32 u, %7, %8, %19, 0x7e; or.b32 t, t, u; and.b32 t, t, 3; setp.ne.u32 p1, t, 0;\n"
                           "setp.ne.u32 p2, %12, %19; setp.ne.u32 p3, %16, %19;\n"
                           "@p0 ld.relaxed.gpu.global.v4.u32 {%1, %2, %3, %4}, [%17];\n"
                           "@p1 ld.relaxed.gpu.global.v4.u32 {%5, %6, %7, %8}, [%17 + 8192];\n"
                           "@p2 ld.relaxed.gpu.global.v4.u32 {%9, %10, %11, %12}, [%18];\n"
                           "@p3 ld.relaxed.gpu.global.v4.u32 {%13, %14, %15, %16}, [%18 + 128];\n"
                           "or.pred p0, p0, p1; or.pred p2, p2, p3; vote.sync.any.pred p0, p0, 0xffffffff; vote.sync.any.pred p2, p2, 0xffffffff;\n"
                           "selp.u32 t, 1, 0, p0; selp.u32 u, 2, 0, p2; or.b32 %0, t, u; }"
                           : "=r"(miss), "+r"(m0.x), "+r"(m0.y), "+r"(m0.z), "+r"(m0.w), "+r"(m1.x), "+r"(m1.y), "+r"(m1.z), "+r"(m1.w),
                             "+r"(r0.x), "+r"(r0.y), "+r"(r0.z), "+r"(r0.w), "+r"(r1.x), "+r"(r1.y), "+r"(r1.z), "+r"(r1.w)
                           : "l"(pm), "l"(pr), "r"(tag) : "memory");
              if (!(miss & 1) && !written) {
                written = true;
                if (!oddw) write_table(par, wg, t7, m0, m1);
                mbar_arrive(bar_mod);
              }
              if (!miss) break;
              watchdog(n);
            }
          }
          const uint32_t zero = r0.w ^ tag;
          auto normalize = [&](uint32_t (&f)[16]) {
#pragma unroll
            for (int k = 0; k < 16; k += 2) { f[k] = ln_norm(f[k], r0.x, r0.y, r0.z); f[k + 1] = ln_norm(f[k + 1], r1.x, r1.y, r1.z); }
          };
          auto modulate = [&](int i, uint32_t (&f)[16]) {
#pragma unroll
            for (int kk = 0; kk < 4; kk++) {
              const uint4 m = lds4(mt + slice_of(i) * 256 + kk * 64);
              f[4 * kk] = hfma2(f[4 * kk], m.x, m.z); f[4 * kk + 1] = hfma2(f[4 * kk + 1], m.x, m.z);
              f[4 * kk + 2] = hfma2(f[4 * kk + 2], m.y, m.w); f[4 * kk + 3] = hfma2(f[4 * kk + 3], m.y, m.w);
            }
            keep(f);
            mbar_arrive_pred(xempty + (i & 3) * 8, l == 0);
          };
          auto publish = [&](int u, uint32_t (&f)[16]) {
#pragma unroll
            for (int kk = 0; kk < 4; kk++) stmatrix4(fa[kk] + OFF_STAGE + u * UNIT, f[4 * kk], f[4 * kk + 1], f[4 * kk + 2], f[4 * kk + 3]);
            __syncwarp();
            mbar_arrive_pred(bar_hpub + u * 8, l == 0);
          };
          auto multiply = [&](int i, uint32_t (&f)[16]) {
            mbar_wait(gfull + (i & 3) * 8, i >> 2);
            const uint64_t db = make_desc(base + (i & 3) * GST_BYTES + UNIT, 8192, 1024);
            wg_fence();
#pragma unroll
            for (int kk = 0; kk < 4; kk++) mma256_rs(ga, gb, f[4 * kk], f[4 * kk + 1], f[4 * kk + 2], f[4 * kk + 3], db + kk * 128);
            wg_commit();
          };
          auto next = [&](int i, uint32_t (&f)[16]) {
            wg_wait<1>();
            mbar_arrive_cl(rempty, GE + ((i + 2) & 3) * 8);
            uint32_t z = zero;
#pragma unroll
            for (int k = 0; k < 16; k += 2) asm volatile("lop3.b32 %0, %1, %2, %0, 0xA8;" : "+r"(z) : "r"(f[k]), "r"(f[k + 1]));
            fetch(i, f, z);
            normalize(f);
            if (i == 3) { keep(f); mbar_wait(bar_mod2, 0); }
            modulate(i, f); multiply(i, f);
          };
          normalize(a[0]);
          keep(a[0]); keep(a[1]);
          mbar_wait(bar_mod, 0);
          PROF(1, tid == 0, 2);
          modulate(0, a[0]); multiply(0, a[0]); publish(0, a[0]);
          keep(a[1]);
          normalize(a[1]);
          modulate(1, a[1]); multiply(1, a[1]);
#pragma unroll 1
          for (int i = 2; i < NRS; i += 2) {
            next(i, a[0]);
            next(i + 1, a[1]);
            if (i == 2) publish(1, a[1]);
          }
          wg_wait<1>();
          mbar_arrive_cl(rempty, GE + ((NRS + 2) & 3) * 8);
#pragma unroll 1
          for (int i = NRS; i < 14; i++) {
            mbar_wait(xfull + (i & 3) * 8, (i >> 2) & 1);
            mbar_wait(gfull + (i & 3) * 8, (i >> 2) & 1);
            const uint32_t xa = base + (i & 3) * GST_BYTES;
            const uint64_t da = make_desc(xa + wg * 8192, 16, 1024), db = make_desc(xa + UNIT, 8192, 1024);
            if (i == 13) bar_sync(2 + wg, 256);
            wg_fence();
#pragma unroll
            for (int kk = 0; kk < 4; kk++) mma256_ss(ga, gb, da + kk * 2, db + kk * 128, 1);
            wg_commit();
            if (i == 13) bar_arrive(3 - wg, 256);
            wg_wait<1>();
            uint32_t z = zero;
#pragma unroll
            for (int k = 0; k < 16; k += 2) asm volatile("lop3.b32 %0, %1, %2, %0, 0xA8;" : "+r"(z) : "r"(a[1][k]), "r"(a[1][k + 1]));
            mbar_arrive_cl(rempty, GE + ((i + 3) & 3) * 8 + z);
            mbar_arrive_pred(xempty + ((i + 3) & 3) * 8, l == 0 && i != NRS);
          }
          mbar_wait(xfull + 16, 1);
          wg_wait<0>();
          keep(ga); keep(gb);
#pragma unroll
          for (int i = 0; i < 64; i++) {
            asm volatile("mov.b32 %0, %1;" : "=f"(s[i]) : "f"(ga[i]));
            asm volatile("mov.b32 %0, %1;" : "=f"(o[i]) : "f"(gb[i]));
          }
        } else {
          float ga[64], gb[64];
#pragma unroll
          for (int i = 0; i < 64; i++) {
            asm volatile("mov.b32 %0, %1;" : "=f"(ga[i]) : "f"(s[i]));
            asm volatile("mov.b32 %0, %1;" : "=f"(gb[i]) : "f"(o[i]));
          }
#pragma unroll 1
          for (int i = 0; i < nst; i++) {
            mbar_wait(gfull + (i & 3) * 8, (i >> 2) & 1);
            const uint64_t da = make_desc(base + unit_of(xt, i & 3) + wg * 8192, 16, 1024), db = make_desc(base + unit_of(wt, i & 3), 8192, 1024);
            if (i == nst - 1) bar_sync(2 + wg, 256);
            wg_fence();
#pragma unroll
            for (int kk = 0; kk < 4; kk++) mma256_ss(ga, gb, da + kk * 2, db + kk * 128, kk ? 1 : i);
            wg_commit();
            if (i == nst - 1) bar_arrive(3 - wg, 256);
            wg_wait<1>();
            mbar_arrive_cl(rempty, GE + ((i + 3) & 3) * 8, i != 0);
            PROF(4, tid == 0 && (i & 3) == 0, 40 + (ps - 1) * 4 + i / 4);
          }
          wg_wait<0>();
          keep(ga); keep(gb);
#pragma unroll
          for (int i = 0; i < 64; i++) {
            asm volatile("mov.b32 %0, %1;" : "=f"(s[i]) : "f"(ga[i]));
            asm volatile("mov.b32 %0, %1;" : "=f"(o[i]) : "f"(gb[i]));
          }
        }
        mbar_arrive_cl(rempty, GE + (ps == 2 ? 24 : 8));
        if (ps == 2) break;
      }
      const uint32_t qw = base + wg * 8192, qt = QT >> (16 * ps), at = ps ? AT1 : AT0;
      {
        const uint32_t wt = ps ? WT1 : WT0;
        const uint64_t da0 = make_desc(qw + unit_of(qt, 2), 16, 1024), da1 = make_desc(qw + unit_of(qt, 3), 16, 1024);
        const uint64_t db0 = make_desc(base + unit_of(wt, 2), 8192, 1024), db1 = make_desc(base + unit_of(wt, 3), 8192, 1024);
        mbar_wait(gfull + 16, 1);
        bar_sync(2 + wg, 256);
        wg_fence();
#pragma unroll
        for (int kk = 0; kk < 4; kk++) mma_ss<1>(s, da0 + kk * 2, db0 + kk * 128, 1);
        wg_commit();
        mbar_wait(xfull + 24, 1);
        mbar_wait(gfull + 24, 1);
        wg_fence();
#pragma unroll
        for (int kk = 0; kk < 4; kk++) mma_ss<1>(s, da1 + kk * 2, db1 + kk * 128, 1);
        wg_commit();
        bar_arrive(3 - wg, 256);
        mbar_wait(ps == 0 ? bar_pread : bar_ofree + 8, 0);
        wg_wait<0>();
        keep(s);
        PROF(2, tid == 0, 8 + ps * 8);
        uint32_t q[32];
        pack_p(s, q);
#pragma unroll
        for (int i = 0; i < 4; i++) stmatrix4((qw + unit_of(qt, 0) + frag_offset(warp)) ^ (i << 5), q[4 * i], q[4 * i + 1], q[4 * i + 2], q[4 * i + 3]);
        keep(q);
        bar_sync(2 + wg, 256);
        wg_fence();
#pragma unroll
        for (int kk = 0; kk < 8; kk++) mma_ss<1>(o, (kk < 4 ? da0 : da1) + (kk & 3) * 2, (kk < 4 ? db0 : db1) + UNIT / 16 + (kk & 3) * 128, 1);
        wg_commit();
        mbar_wait(bfull, 0);
        wg_fence();
        const uint64_t dk = make_desc(base + unit_of(at, 0), 16, 1024);
#pragma unroll
        for (int kk = 0; kk < 8; kk++) mma_rs<0>(s, q[4 * kk], q[4 * kk + 1], q[4 * kk + 2], q[4 * kk + 3], dk + (kk >> 2) * 1024 + (kk & 3) * 2, kk != 0);
        wg_commit();
        bar_arrive(3 - wg, 256);
#pragma unroll
        for (int i = 4; i < 8; i++) stmatrix4((qw + unit_of(qt, 1) + frag_offset(warp)) ^ ((i & 3) << 5), q[4 * i], q[4 * i + 1], q[4 * i + 2], q[4 * i + 3]);
        wg_wait<1>();
        keep(o);
        mbar_arrive_cl(rempty, GE + 16);
        mbar_arrive_cl(rempty, GE + 24);
        store_chunk<0>(o, qw + unit_of(qt, 2) + frag_offset(warp));
        store_chunk<1>(o, qw + unit_of(qt, 3) + frag_offset(warp));
        wg_wait<0>();
        keep(s);
        mbar_arrive_cl(rempty, 0);
      }
      PROF(4, tid == 0 && ps == 1, 61);
      float l0 = 0.f, l1 = 0.f, f0 = 0.f, f1 = 0.f;
      auto step = [&](auto odd_c, const int j, uint32_t (&pw)[32], uint32_t (&pr)[32]) {
        constexpr bool ODD = decltype(odd_c)::value;
        const bool first = !ODD && (j & 2) == 0, last = ODD && j == 7;
        const uint32_t ph = (j >> 1) & 1;
        float i0, i1, a0, a1;
        const bool so = !ODD && j == 4;
        if (so) { i0 = inv_quad_sum(l0); i1 = inv_quad_sum(l1); l0 = 0.f; l1 = 0.f; }
        if (first) {
          int m0 = max(__float_as_int(s[0]), __float_as_int(s[1])), m1 = max(__float_as_int(s[2]), __float_as_int(s[3]));
#pragma unroll
          for (int i = 1; i < 16; i++) {
            m0 = __vimax3_s32(m0, __float_as_int(s[4 * i]), __float_as_int(s[4 * i + 1]));
            m1 = __vimax3_s32(m1, __float_as_int(s[4 * i + 2]), __float_as_int(s[4 * i + 3]));
          }
          m0 = max(m0, __shfl_xor_sync(0xffffffffu, m0, 1)); m1 = max(m1, __shfl_xor_sync(0xffffffffu, m1, 1));
          m0 = max(m0, __shfl_xor_sync(0xffffffffu, m0, 2)); m1 = max(m1, __shfl_xor_sync(0xffffffffu, m1, 2));
          f0 = fmaf(__int_as_float(m0), SCL2, BIAS); f1 = fmaf(__int_as_float(m1), SCL2, BIAS);
        }
        bool redo = false;
        while (true) {
          if (redo) {
            float m0 = fmaxf(s[0], s[1]), m1 = fmaxf(s[2], s[3]);
#pragma unroll
            for (int i = 1; i < 16; i++) { m0 = fmaxf(m0, fmaxf(s[4 * i], s[4 * i + 1])); m1 = fmaxf(m1, fmaxf(s[4 * i + 2], s[4 * i + 3])); }
            m0 = fmaxf(m0, __shfl_xor_sync(0xffffffffu, m0, 1)); m1 = fmaxf(m1, __shfl_xor_sync(0xffffffffu, m1, 1));
            m0 = fmaxf(m0, __shfl_xor_sync(0xffffffffu, m0, 2)); m1 = fmaxf(m1, __shfl_xor_sync(0xffffffffu, m1, 2));
            m0 = fmaf(m0, SCL2, BIAS); m1 = fmaf(m1, SCL2, BIAS);
            if (!first) {
              m0 = fmaxf(m0, f0); m1 = fmaxf(m1, f1);
              const float c0 = ex2(f0 - m0), c1 = ex2(f1 - m1);
              l0 *= c0; l1 *= c1;
              wg_wait<0>();
              keep(o);
#pragma unroll
              for (int i = 0; i < 16; i++) { o[4 * i] *= c0; o[4 * i + 1] *= c0; o[4 * i + 2] *= c1; o[4 * i + 3] *= c1; }
            }
            f0 = m0; f1 = m1;
          }
          float b0 = 0.f, b1 = 0.f;
          a0 = 0.f; a1 = 0.f;
#pragma unroll
          for (int i = 0; i < 16; i++) {
            const float e0 = ex2(fmaf(s[4 * i], SCL2, -f0)), e1 = ex2(fmaf(s[4 * i + 1], SCL2, -f0));
            const float e2 = ex2(fmaf(s[4 * i + 2], SCL2, -f1)), e3 = ex2(fmaf(s[4 * i + 3], SCL2, -f1));
            a0 += e0; b0 += e1; a1 += e2; b1 += e3;
            pw[2 * i] = pack_bf(e0, e1); pw[2 * i + 1] = pack_bf(e2, e3);
            if (i == VREL) {
#pragma unroll
              for (int k = 0; k < 2 * VREL + 2; k++) asm volatile("" : "+r"(pw[k])::"memory");
              mbar_wait(bar_mod, 0);
              wg_wait<0>();
              mbar_arrive_cl(rempty, ODD ? 16 : 0, !redo && (ODD || j));
#pragma unroll
              for (int k = 4 * VREL + 4; k < 64; k++) asm volatile("" : "+f"(s[k])::"memory");
            }
          }
          a0 += b0; a1 += b1;
          if (redo) break;
          redo = __any_sync(0xffffffffu, !(a0 + a1 < 1.f));
          if (!redo) break;
        }
        l0 += a0; l1 += a1;
        keep(pw);
        keep(o);
        if (so) store_chunk<0>(o, i0, i1, qw + unit_of(qt, 0) + frag_offset(warp));
        keep(o);
        if (j == (ODD ? 5 : 0)) { fence_async_smem(); if (ODD) mbar_arrive(bar_ofull + wg * 8); }
        mbar_wait(bfull + (ODD ? 24 : 8), ph);
        bar_sync(2 + wg, 256);
        if (!last) {
          const uint32_t qn = qt >> (j >= 3 ? 8 : 0);
          wg_fence();
          issue_qk(s, qw + unit_of(qn, 0), qw + unit_of(qn, 1), base + unit_of(at, ODD ? 3 : 1));
          wg_commit();
          mbar_wait(bfull + (ODD ? 0 : 16), ODD ? ph ^ 1 : ph);
        }
        if (so) { store_chunk<1>(o, i0, i1, qw + unit_of(qt, 1) + frag_offset(warp)); keep(o); }
        wg_fence();
        issue_pv(o, pw, base + unit_of(at, ODD ? (last ? 3 : 0) : 2), !first);
        wg_commit();
        bar_arrive(3 - wg, 256);
        wg_wait<1>();
        keep(s);
        mbar_arrive_cl(rempty, ODD ? 24 : 8, !last);
        PROF(4, tid == 0 && ps == 1, 51 + j);
      };
      uint32_t pa[32], pb[32];
#pragma unroll 1
      for (int j = 0; j < 8; j += 2) {
        step(std::false_type{}, j, pa, pb);
        step(std::true_type{}, j + 1, pb, pa);
      }
      {
        const float i0 = inv_quad_sum(l0), i1 = inv_quad_sum(l1);
        wg_wait<0>();
        keep(o);
        mbar_arrive_cl(rempty, 24);
        store_chunk<0>(o, i0, i1, qw + unit_of(qt, 2) + frag_offset(warp));
        store_chunk<1>(o, i0, i1, qw + unit_of(qt, 3) + frag_offset(warp));
        fence_async_smem();
        mbar_arrive(bar_ofull + 16 + wg * 8);
      }
      PROF(2, tid == 0, 10 + ps * 8);
    }

    const int ln = fresh_lane(), g = ln >> 2, tq = ln & 3, ct = warp * 32 + ln;
    const bool lane0 = ln == 0;
    const int lrow0 = warp * 16 + g;
    const uint32_t res = base + OFF_RES, trow = res + wg * 8192 + frag_offset(warp);
    uint32_t xr[32];
    uint4 sv[4], own;
    uint32_t* const sg = g_stats + (rb * 8 + warp) * 512 + g * 4;
    uint32_t* sp[4];
#pragma unroll
    for (int k = 0; k < 4; k++) sp[k] = sg + (tq & 1) * 32 + (((tq >> 1) ^ (cj >> 2)) * 4 + (k ^ (cj & 3))) * 64;
    {
      const uint64_t da = make_desc(base + wg * 8192, 16, 1024), db = make_desc(base, 8192, 1024);
      constexpr int U = UNIT / 16;
#define HALF_STAGE(acc, xu, wu) _Pragma("unroll") for (int kk = 0; kk < 4; kk++) mma_ss<1>(acc, da + (xu) * U + kk * 2, db + (wu) * U + kk * 128, 1)
      PROF(10, ct == PT, 19); STAMP(0);
      cluster_arrive();
      mbar_wait(gfull, 1);
      mbar_wait(gfull + 8, 1);
      bar_sync(2 + wg, 256);
      wg_fence();
      HALF_STAGE(o, 7, 1);
      HALF_STAGE(o, 8, 3);
      wg_commit();
      STAMP(16);
      mbar_wait(gfull + 16, 1);
      STAMP(17);
      wg_fence();
      HALF_STAGE(o, 6, 11);
      wg_commit();
      bar_arrive(3 - wg, 256);
      mbar_wait(bar_par, 0);
      uint32_t* xo = g_xch + ((size_t)b * 8 * 256 + ct) * 4;
      const uint32_t* xi = g_xch + ((size_t)(b ^ 2) * 8 * 256 + ct) * 4;
      const uint32_t par1 = (~lds1(par + PAR_CONST + 4) & 1) << 16;
      wg_wait<1>();
      mbar_arrive_pred(bar_rel, lane0);
      wg_wait<0>();
      keep(o);
      mbar_arrive_pred(bar_ring, lane0);
      PROF(8, ct == PT, 20); STAMP(1);
#define SEND(i) st_b128(xo + (i) * 1024, (pack_bf(o[8 * (i)], o[8 * (i) + 1]) & ~0x10000u) | par1, pack_bf(o[8 * (i) + 2], o[8 * (i) + 3]), \
                        pack_bf(o[8 * (i) + 4], o[8 * (i) + 5]), pack_bf(o[8 * (i) + 6], o[8 * (i) + 7]))
#pragma unroll
      for (int i = 0; i < NS1; i++) SEND(i);
      PROF(8, ct == PT, 21); STAMP(2);
      bar_sync(2 + wg, 256);
      wg_fence();
      HALF_STAGE(s, 7, 0);
      HALF_STAGE(s, 8, 2);
      HALF_STAGE(s, 6, 10);
      wg_commit();
      bar_arrive(3 - wg, 256);
      STAMP(18);
      mbar_wait(gfull + 24, 1);
#pragma unroll
      for (int i = NS1; i < 8; i++) SEND(i);
      uint4 v[8];
      STAMP(19);
      mbar_wait(bar_xres, 0);
      wg_wait<0>();
      mbar_arrive_pred(bar_ring + 8, lane0);
      bar_sync(2 + wg, 256);
      STAMP(20);
#pragma unroll
      for (int i = 0; i < LD2; i++) v[i] = ld_b128(xi + i * 1024);
      mbar_wait(bar_xres, 0);
      wg_fence();
      HALF_STAGE(s, 9, 4);
      wg_commit();
      mbar_wait(bar_rx, 0);
      wg_fence();
      HALF_STAGE(s, 1, 5);
      wg_commit();
      bar_arrive(3 - wg, 256);
      STAMP(21);
#pragma unroll
      for (int i = LD2; i < 8; i++) v[i] = ld_b128(xi + i * 1024);
      mbar_wait(bar_xres, 0);
      wg_wait<0>();
      keep(s);
      mbar_arrive_pred(bar_ring + 16, lane0);
      PROF(10, ct == PT, 23); STAMP(4);
#pragma unroll
      for (int i = 0; i < 16; i += 2) ldmatrix4((trow ^ ((i & 7) << 4)) + (i >> 3) * 16384, xr[2 * i], xr[2 * i + 1], xr[2 * i + 2], xr[2 * i + 3]);
      uint32_t ga[16];
      uint4 bw[8];
#pragma unroll
      for (int i = 0; i < 8; i++) {
        if (!(i & 1)) {
          const uint4 t = lds4(par + PAR_SINK + i * 32 + tq * 16);
          ga[2 * i] = t.x; ga[2 * i + 1] = t.y; ga[2 * i + 2] = t.z; ga[2 * i + 3] = t.w;
        }
        bw[i] = lds4(par + PAR_T1 + i * 64 + tq * 16);
        if (!(g & 1)) { bw[i].x = 0x3f803f80u; bw[i].y = 0x3f803f80u; }
      }
      uint32_t pk[32];
      pack_p(s, pk);
      const uint32_t par2 = (~lds1(par + PAR_CONST + 12) & 1) << 16;
      {
        uint32_t n = 0, miss;
        do {
          miss = 0;
#pragma unroll
          for (int i = 0; i < 8; i++) miss |= v[i].x ^ par2;
          miss = __any_sync(0xffffffffu, miss & 0x10000u);
          if (miss) {
#pragma unroll
            for (int i = 0; i < 8; i++)
              asm volatile("{ .reg .pred p; .reg .b32 t; xor.b32 t, %0, %5; and.b32 t, t, 0x10000; setp.ne.u32 p, t, 0;\n"
                           "@p ld.relaxed.gpu.global.v4.u32 {%0, %1, %2, %3}, [%4]; }"
                           : "+r"(v[i].x), "+r"(v[i].y), "+r"(v[i].z), "+r"(v[i].w) : "l"(xi + i * 1024), "r"(par1) : "memory");
          }
          watchdog(n);
        } while (miss);
      }
      PROF(8, ct == PT, 22); STAMP(3);
      float ds[4] = {0.f, 0.f, 0.f, 0.f}, dl[4] = {0.f, 0.f, 0.f, 0.f}, q0[4] = {0.f, 0.f, 0.f, 0.f}, q1[4] = {0.f, 0.f, 0.f, 0.f};
#pragma unroll
      for (int i = 0; i < 8; i++) {
        const uint32_t u0 = hfma2(ga[2 * i], hadd2(pk[4 * i], v[i].x & ~0x10000u), xr[4 * i]);
        const uint32_t u1 = hfma2(ga[2 * i], hadd2(pk[4 * i + 1], v[i].y), xr[4 * i + 1]);
        const uint32_t u2 = hfma2(ga[2 * i + 1], hadd2(pk[4 * i + 2], v[i].z), xr[4 * i + 2]);
        const uint32_t u3 = hfma2(ga[2 * i + 1], hadd2(pk[4 * i + 3], v[i].w), xr[4 * i + 3]);
        xr[4 * i] = u0; xr[4 * i + 1] = u1; xr[4 * i + 2] = u2; xr[4 * i + 3] = u3;
        mma16816(ds, u0, u1, u2, u3, bw[i].x, bw[i].y);
        mma16816(dl, u0, u1, u2, u3, bw[i].z, bw[i].w);
        mma16816(q0, u0, u1, u2, u3, u0, u2);
        mma16816(q1, u0, u1, u2, u3, u1, u3);
      }
      const float sqa = (g & 1) ? q0[1] : q0[0], sqb = (g & 1) ? q1[3] : q1[2], dta = ds[1] + dl[1], dtb = ds[3] + dl[3];
      if (tq == (g >> 1)) {
        st_b128(sg + cj * 64, __float_as_uint(ds[0]), __float_as_uint(sqa), __float_as_uint(dta), tag);
        st_b128(sg + cj * 64 + 32, __float_as_uint(ds[2]), __float_as_uint(sqb), __float_as_uint(dtb), tag);
      }
#pragma unroll
      for (int k = 0; k < 4; k++) sv[k] = ld_b128(sp[k]);
      mbar_wait(bar_xres, 0);
      const float sqc = __shfl_sync(0xffffffffu, sqa, g * 4 + (g >> 1)), sqd = __shfl_sync(0xffffffffu, sqb, g * 4 + (g >> 1));
      own = (tq & 1) ? make_uint4(__float_as_uint(ds[2]), __float_as_uint(sqd), __float_as_uint(dtb), tag)
                     : make_uint4(__float_as_uint(ds[0]), __float_as_uint(sqc), __float_as_uint(dta), tag);
    }
    PROF(8, ct == PT, 29); STAMP(5);
    uint32_t mm, ih, il;
    float rbest;
    uint32_t wf[128];
    const uint32_t frow = (ln & 7) + (ln >> 4) * 8;
    const uint32_t wfo = base + (warp & 1) * 8192 + frow * 64 + ((((ln >> 3) & 1) ^ ((frow >> 1) & 3)) << 4);
#define LOAD_WF(m) _Pragma("unroll") for (int f = 0; f < 16; f++) {                                                   \
      const int r = ((f >> 1) * 4 + (m) * 2 + (f & 1)) * 4;                                                           \
      ldmatrix4t(((wfo + unit_of((m) ? FT_U : FT_G, warp >> 1)) ^ ((f & 1) * 32)) + (f >> 1) * 1024, wf[r], wf[r + 1], wf[r + 2], wf[r + 3]); \
    }
    bool early;
    {
#pragma unroll
      for (int i = 0; i < 16; i += 2) stmatrix4((trow ^ ((i & 7) << 4)) + (i >> 3) * 16384, xr[2 * i], xr[2 * i + 1], xr[2 * i + 2], xr[2 * i + 3]);
      const uint4 cst = lds4(par + PAR_CONST);
      const float A1 = __uint_as_float(cst.x), A2 = __uint_as_float(cst.z);
      uint32_t n = 0;
      early = false;
#pragma unroll 1
      while (true) {
        if (!early && (b >= NFFN || __all_sync(0xffffffffu, mbar_test(bar_box + (warp >> 1) * 8, 0)))) {
          early = true;
          LOAD_WF(0);
          __syncwarp();
          mbar_arrive_pred(bar_gate, lane0);
        }
        uint32_t miss;
        asm volatile("{ .reg .pred p0, p1, p2, p3; .reg .b64 u, v; .reg .b128 w;\n"
                     "setp.ge.u32 p0, %22, 2; setp.ne.and.u32 p0, %4, %21, p0; setp.ne.u32 p1, %8, %21; setp.ne.u32 p2, %12, %21; setp.ne.u32 p3, %16, %21;\n"
                     "@p0 ld.relaxed.gpu.global.v4.u32 {%1, %2, %3, %4}, [%17];\n"
                     "@p1 ld.relaxed.gpu.global.v4.u32 {%5, %6, %7, %8}, [%18];\n"
                     "@p2 ld.relaxed.gpu.global.v4.u32 {%9, %10, %11, %12}, [%19];\n"
                     "@p3 ld.relaxed.gpu.global.v4.u32 {%13, %14, %15, %16}, [%20];\n"
                     "or.pred p0, p0, p1; or.pred p2, p2, p3; or.pred p0, p0, p2; vote.sync.any.pred p0, p0, 0xffffffff; selp.u32 %0, 1, 0, p0; }"
                     : "=r"(miss), "+r"(sv[0].x), "+r"(sv[0].y), "+r"(sv[0].z), "+r"(sv[0].w), "+r"(sv[1].x), "+r"(sv[1].y), "+r"(sv[1].z), "+r"(sv[1].w),
                       "+r"(sv[2].x), "+r"(sv[2].y), "+r"(sv[2].z), "+r"(sv[2].w), "+r"(sv[3].x), "+r"(sv[3].y), "+r"(sv[3].z), "+r"(sv[3].w)
                     : "l"(sp[0]), "l"(sp[1]), "l"(sp[2]), "l"(sp[3]), "r"(tag), "r"(tq) : "memory");
        if (!miss) break;
        watchdog(n);
      }
      const uint4 v0 = tq < 2 ? own : sv[0], v1 = sv[1], v2 = sv[2], v3 = sv[3];
      PROF(8, ct == PT, 30); STAMP(6);
      float su = (__uint_as_float(v0.x) + __uint_as_float(v1.x)) + (__uint_as_float(v2.x) + __uint_as_float(v3.x));
      float sq = (__uint_as_float(v0.y) + __uint_as_float(v1.y)) + (__uint_as_float(v2.y) + __uint_as_float(v3.y));
      float dt = (__uint_as_float(v0.z) + __uint_as_float(v1.z)) + (__uint_as_float(v2.z) + __uint_as_float(v3.z));
      su += __shfl_xor_sync(0xffffffffu, su, 2); sq += __shfl_xor_sync(0xffffffffu, sq, 2); dt += __shfl_xor_sync(0xffffffffu, dt, 2);
      const float m = su * (1.f / DM);
      float mb, sd;
      ln_scalars(m, fmaxf(sq * (1.f / DM) - m * m, 0.f), mb, sd);
      const float inv = rcp(sd);
      rbest = (dt - mb * A1) * inv + A2;
      mm = pack_bf(mb, mb);
      ih = pack_bf(inv, inv);
      const float lo = inv - bf_lo(ih);
      il = pack_bf(lo, lo);
    }
    int ibest;
    {
      const uint32_t bits = __float_as_uint(rbest);
      const uint32_t key = (((int)bits < 0 ? ~bits : bits | 0x80000000u) & ~0x1ffu) | ((127 - lrow0 - (tq & 1) * 8) << 2) | tag;
      sts1(par + PAR_RED + warp * 4, __reduce_max_sync(0xffffffffu, key));
      PROF(8, ct == PT, 38); STAMP(7);
      bar_sync(1, 256);
      const uint4 ka = lds4(par + PAR_RED), kb = lds4(par + PAR_RED + 16);
      const uint32_t k2 = max(max(max(ka.x, ka.y), max(ka.z, ka.w)), max(max(kb.x, kb.y), max(kb.z, kb.w)));
      if (ct < CR && cj == 0) st_relaxed(g_cand + ct * 512 + rb * CS, k2);
      ibest = 127 - ((k2 >> 2) & 127);
    }
    PROF(8, ct == PT, 39); STAMP(8);
    if ((ibest >> 4) == warp) {
      const int src = (ibest & 7) * 4 + ((ibest >> 3) & 1), ch = g * 2;
      const uint32_t cm = __shfl_sync(0xffffffffu, mm, src), ch_ = __shfl_sync(0xffffffffu, ih, src), cl = __shfl_sync(0xffffffffu, il, src);
      const uint32_t xa = res + (ch >> 3) * 16384 + ibest * 128 + (((ch & 7) ^ (ibest & 7)) << 4) + tq * 4;
      const uint32_t x0 = lds1(xa), x1 = lds1(xa ^ 16);
      const uint2 p0 = lds2(par + PAR_T2 + ch * 64 + tq * 16), p1 = lds2(par + PAR_T2 + ch * 64 + 64 + tq * 16);
      uint32_t* dst = g_row + rb * 2 * DM + cj * 128 + ln * 4;
      st_pairs(dst, ln_mod(x0, cm, ch_, cl, p0.x, p0.y), ln_mod(x1, cm, ch_, cl, p1.x, p1.y), tag);
      st_pairs(dst + DM, x0, x1, tag);
      __syncwarp();
    }
    PROF(8, ct == PT, 37); STAMP(9);
    uint32_t wd[64];
    const uint32_t wda = base + unit_of(FT_D, warp >> 1) + (warp & 1) * 8192 + frow * 128 + ((((ln >> 3) & 1) ^ (ln & 7)) << 4);
#define LOAD_WD(f) ldmatrix4t((wda ^ ((((f) >> 1) & 3) * 32)) + ((f) >> 3) * 4096 + ((f) & 1) * 2048, wd[4 * (f)], wd[4 * (f) + 1], wd[4 * (f) + 2], wd[4 * (f) + 3])
    if (!early) {
      if (b < NFFN) mbar_wait(bar_box + (warp >> 1) * 8, 0);
      LOAD_WF(0);
      __syncwarp();
      mbar_arrive_pred(bar_gate, lane0);
    }
    if (b < NFFN) {
      const uint32_t own = base + unit_of(FT_G, warp >> 1) + (warp & 1) * 8192;
      mbar_wait(bar_box + (4 + (warp >> 1)) * 8, 0);
      LOAD_WF(1);
      uint32_t* const ydst = ypart_slot(b, warp * 16 + (tq & 1) * 8 + g);
      PROF(8, ct == PT, 31); STAMP(10);
      bool wdok;
      {
        uint32_t n = 0;
        while (!(wdok = __all_sync(0xffffffffu, mbar_test(bar_box + (8 + (warp >> 1)) * 8, 0))) && !__all_sync(0xffffffffu, mbar_test(bar_sel, 0))) watchdog(n);
      }
      if (wdok) {
#pragma unroll
        for (int f = 0; f < 16; f++) LOAD_WD(f);
      }
      STAMP(11);
      mbar_wait(bar_sel, 0);
      PROF(8, ct == PT, 33); STAMP(12);
      float d[8][4];
#pragma unroll
      for (int i = 0; i < 4; i++) { d[i][0] = 0.f; d[i][1] = 0.f; d[i][2] = 0.f; d[i][3] = 0.f; }
#pragma unroll
      for (int ks = 0; ks < 8; ks++) {
        const uint2 hb = lds2(own + 256 + ks * 32 + tq * 8);
#pragma unroll
        for (int mt = 0; mt < 4; mt++) {
          const int r = ks * 16 + mt * 4;
          mma16816(d[mt], wf[r], wf[r + 1], wf[r + 2], wf[r + 3], hb.x, hb.y);
        }
      }
      sts2(own + (tq * 8 + g) * 8, __float_as_uint((tq & 2) ? ((tq & 1) ? d[1][2] : d[1][0]) : ((tq & 1) ? d[0][2] : d[0][0])),
           __float_as_uint((tq & 2) ? ((tq & 1) ? d[3][2] : d[3][0]) : ((tq & 1) ? d[2][2] : d[2][0])));
      bar_sync(1, 256);
      uint32_t ab[4];
      {
        uint2 pv[8];
#pragma unroll
        for (int w8 = 0; w8 < 8; w8++) pv[w8] = lds2(base + ln * 8 + ((FT_G >> (w8 >> 1) * 4) & 15) * UNIT + (w8 & 1) * 8192);
#define SUM4(i, c) ((__uint_as_float(pv[i].c) + __uint_as_float(pv[i + 1].c)) + (__uint_as_float(pv[i + 2].c) + __uint_as_float(pv[i + 3].c)))
        const float G = SUM4(0, x) + SUM4(4, x), U = SUM4(0, y) + SUM4(4, y);
        const float act = rbf(silu_f(rbf(G))) * rbf(U);
        const uint32_t pk = pack_bf(act, __shfl_down_sync(0xffffffffu, act, 1));
#pragma unroll
        for (int i = 0; i < 4; i++) ab[i] = __shfl_sync(0xffffffffu, pk, i * 8 + tq * 2);
      }
      if (!wdok) {
        mbar_wait(bar_box + (8 + (warp >> 1)) * 8, 0);
#pragma unroll
        for (int f = 0; f < 16; f++) LOAD_WD(f);
      }
      PROF(8, ct == PT, 34); STAMP(13);
#pragma unroll
      for (int mt = 0; mt < 8; mt++) {
        d[mt][0] = 0.f; d[mt][1] = 0.f; d[mt][2] = 0.f; d[mt][3] = 0.f;
        mma16816(d[mt], wd[mt * 8], wd[mt * 8 + 1], wd[mt * 8 + 2], wd[mt * 8 + 3], ab[0], ab[1]);
        mma16816(d[mt], wd[mt * 8 + 4], wd[mt * 8 + 5], wd[mt * 8 + 6], wd[mt * 8 + 7], ab[2], ab[3]);
      }
      uint32_t yw[4];
#pragma unroll
      for (int i = 0; i < 4; i++) yw[i] = (tq & 1) ? pack_bf(d[2 * i][2], d[2 * i + 1][2]) : pack_bf(d[2 * i][0], d[2 * i + 1][0]);
      if (tq < 2) st_b128(ydst, (yw[0] & ~1u) | (tag & 1), (yw[1] & ~1u) | (tag >> 1), yw[2], yw[3]);
      PROF(8, ct == PT, 35); STAMP(14);
    }
    mbar_wait(bar_sel, 0);
    mbar_arrive_pred(bar_win, ct == 0);
    const int iwin = lds1(par + PAR_CONST + 60) & 0x7ff;
    const bool cand = (iwin >> 4) == rb * 8 + warp;
    {
      const uint32_t mm0 = __shfl_sync(0xffffffffu, mm, ln & ~1), mm1 = __shfl_sync(0xffffffffu, mm, ln | 1);
      const uint32_t ih0 = __shfl_sync(0xffffffffu, ih, ln & ~1), ih1 = __shfl_sync(0xffffffffu, ih, ln | 1);
      const uint32_t il0 = __shfl_sync(0xffffffffu, il, ln & ~1), il1 = __shfl_sync(0xffffffffu, il, ln | 1);
#pragma unroll 1
      for (int hf = 0; hf < 2; hf++) {
        uint32_t x[16];
#pragma unroll
        for (int i = 0; i < 8; i += 2) ldmatrix4((trow ^ (i << 4)) + hf * 16384, x[2 * i], x[2 * i + 1], x[2 * i + 2], x[2 * i + 3]);
#pragma unroll
        for (int i = 0; i < 8; i++) {
          const uint4 pv = lds4(par + PAR_T2 + (hf * 8 + i) * 64 + tq * 16);
          x[2 * i] = hfma2(hfma2(ln_norm(x[2 * i], mm0, ih0, il0), pv.x, pv.y), pv.z, x[2 * i]);
          x[2 * i + 1] = hfma2(hfma2(ln_norm(x[2 * i + 1], mm1, ih1, il1), pv.x, pv.y), pv.z, x[2 * i + 1]);
        }
#pragma unroll
        for (int i = 0; i < 8; i += 2) stmatrix4((trow ^ (i << 4)) + hf * 16384, x[2 * i], x[2 * i + 1], x[2 * i + 2], x[2 * i + 3]);
        if (!cand) fence_async_smem();
        __syncwarp();
        if (!cand && elect_one()) {
          tma2d_store(&maps.out, res + hf * 16384 + warp * 2048, cj * 128 + hf * 64, rb * 128 + warp * 16);
          asm volatile("cp.async.bulk.commit_group;" ::: "memory");
        }
      }
    }
    if (cand) {
      const int wrow0 = warp * 16;
#pragma unroll 2
      for (int p = 0; p < 8; p++) {
        const int row = 2 * p + (ln >> 4), ch = ln & 15;
        const uint4 v = lds4(res + (ch >> 3) * 16384 + (wrow0 + row) * 128 + (((ch & 7) ^ (row & 7)) << 4));
        if (rb * 128 + wrow0 + row != iwin) *reinterpret_cast<uint4*>(P.out + (size_t)(rb * 128 + wrow0 + row) * DM + cj * 128 + ch * 8) = v;
      }
    }
    asm volatile("cp.async.bulk.wait_group.read 0;" ::: "memory");
    PROF(8, ct == PT, 11); STAMP(15);
    cluster_wait();
  }
}

typedef CUresult (*EncodeFn)(CUtensorMap*, CUtensorMapDataType, cuuint32_t, void*, const cuuint64_t*, const cuuint64_t*,
                             const cuuint32_t*, const cuuint32_t*, CUtensorMapInterleave, CUtensorMapSwizzle,
                             CUtensorMapL2promotion, CUtensorMapFloatOOBfill);

void map2d(EncodeFn enc, CUtensorMap* m, const void* p, uint64_t rows, uint64_t cols, uint32_t brows) {
  cuuint64_t dims[2] = {cols, rows}, strides[1] = {cols * 2};
  cuuint32_t box[2] = {64, brows}, es[2] = {1, 1};
  enc(m, CU_TENSOR_MAP_DATA_TYPE_BFLOAT16, 2, const_cast<void*>(p), dims, strides, box, es, CU_TENSOR_MAP_INTERLEAVE_NONE,
      CU_TENSOR_MAP_SWIZZLE_128B, CU_TENSOR_MAP_L2_PROMOTION_L2_256B, CU_TENSOR_MAP_FLOAT_OOB_FILL_NONE);
}
void map2d_narrow(EncodeFn enc, CUtensorMap* m, const void* p, uint64_t rows, uint64_t cols, uint32_t brows) {
  cuuint64_t dims[2] = {cols, rows}, strides[1] = {cols * 2};
  cuuint32_t box[2] = {32, brows}, es[2] = {1, 1};
  enc(m, CU_TENSOR_MAP_DATA_TYPE_BFLOAT16, 2, const_cast<void*>(p), dims, strides, box, es, CU_TENSOR_MAP_INTERLEAVE_NONE,
      CU_TENSOR_MAP_SWIZZLE_64B, CU_TENSOR_MAP_L2_PROMOTION_L2_64B, CU_TENSOR_MAP_FLOAT_OOB_FILL_NONE);
}
void map3d(EncodeFn enc, CUtensorMap* m, const void* p, uint64_t rows, uint64_t cols, uint32_t brows, uint32_t nch) {
  cuuint64_t dims[3] = {64, rows, cols / 64}, strides[2] = {cols * 2, 128};
  cuuint32_t box[3] = {64, brows, nch}, es[3] = {1, 1, 1};
  enc(m, CU_TENSOR_MAP_DATA_TYPE_BFLOAT16, 3, const_cast<void*>(p), dims, strides, box, es, CU_TENSOR_MAP_INTERLEAVE_NONE,
      CU_TENSOR_MAP_SWIZZLE_128B, CU_TENSOR_MAP_L2_PROMOTION_L2_256B, CU_TENSOR_MAP_FLOAT_OOB_FILL_NONE);
}

}

extern "C" void kernel_launch(void* const* d_in, const int* in_sizes, int n_in, void* d_out, int out_size) {
  (void)in_sizes; (void)n_in; (void)out_size;
  static EncodeFn enc = nullptr;
  if (!enc) {
    void* fn = nullptr;
    cudaDriverEntryPointQueryResult st;
    cudaGetDriverEntryPoint("cuTensorMapEncodeTiled", &fn, cudaEnableDefault, &st);
    enc = (EncodeFn)fn;
    cudaFuncSetAttribute(fused_kernel, cudaFuncAttributeMaxDynamicSharedMemorySize, SMEM_BYTES);
  }
  Maps maps;
  map2d(enc, &maps.x, d_in[0], SEQ, DM, 128);
  map2d(enc, &maps.out, d_out, SEQ, DM, 16);
  map3d(enc, &maps.wq, d_in[3], DM, NQ, 64, 2);
  map3d(enc, &maps.k, d_in[1], 4 * SK, 128, 128, 1);
  map3d(enc, &maps.v, d_in[2], 4 * SK, 128, 128, 1);
  map3d(enc, &maps.wo, d_in[4], NQ, DM, 64, 2);
  map2d_narrow(enc, &maps.wg, d_in[7], DM, FF, 256);
  map2d_narrow(enc, &maps.wu, d_in[8], DM, FF, 256);
  map3d(enc, &maps.wd, d_in[9], FF, DM, 32, 4);
  map2d_narrow(enc, &maps.wm, d_in[11], DM, NMOD, 256);
  Ptrs p;
  p.x = (const __nv_bfloat16*)d_in[0];
  p.w_r = (const __nv_bfloat16*)d_in[6];
  p.w_gate = (const __nv_bfloat16*)d_in[7];
  p.w_up = (const __nv_bfloat16*)d_in[8];
  p.w_down = (const __nv_bfloat16*)d_in[9];
  p.c = (const __nv_bfloat16*)d_in[10];
  p.w_mod = (const __nv_bfloat16*)d_in[11];
  p.out = (__nv_bfloat16*)d_out;
  fused_kernel<<<NMAIN + NHELP, 384, SMEM_BYTES>>>(p, maps);
}
```
